```python
import torch

def _softmax(x, axis=-1):
    return torch.softmax(x, dim=axis)
def _gelu(x):
    return torch.nn.functional.gelu(x, approximate="tanh")
def _silu(x):
    return torch.nn.functional.silu(x)
def _sigmoid(x):
    return torch.sigmoid(x)
def _layernorm(x, axis=-1, eps=1e-5):
    m = x.mean(dim=axis, keepdim=True)
    v = x.var(dim=axis, keepdim=True, unbiased=False)
    return (x - m) / torch.sqrt(v + eps)
def _scatter_add(tgt, idx, src, axis=0):
    return tgt.clone().index_add_(axis, idx, src)
def _segment_sum(src, seg, n):
    out = torch.zeros((n,) + src.shape[1:], dtype=src.dtype)
    return out.index_add_(0, seg, src)
def _pad(x, pw):
    flat = tuple(v for pair in reversed(pw) for v in pair)
    return torch.nn.functional.pad(x, flat)

kernel_name = 'interleave_layers__sliding_local_dilated__ssm_conv_s4d__prompt'

def setup_inputs():

    _w = (lambda a: (lambda t: t.to(torch.bfloat16) if t.is_floating_point() else t)(torch.as_tensor(a)))
    def _A_setup():
        B, S, D = 1, 2048, 640
        return {
            "x": _w((lambda *s: torch.randn(*s, dtype=torch.bfloat16) * 0.05)(B, S, D)),
            "wqkv": _w((lambda *s: torch.randn(*s, dtype=torch.bfloat16) * 0.05)(D, 3 * D)),
            "wo": _w((lambda *s: torch.randn(*s, dtype=torch.bfloat16) * 0.05)(D, D)),
        }
    _A_in = _A_setup()

    def _B_setup():
        Bsz, L, D, N = 1, 2048, 640, 192
        return {
            "u": _w((lambda *s: torch.randn(*s, dtype=torch.bfloat16) * 0.05)(Bsz, L, D)),
            "log_A_real": _w((lambda *s: torch.randn(*s, dtype=torch.bfloat16) * 3.2)(D, N) * 0.5),
            "A_imag": _w((lambda *s: torch.randn(*s, dtype=torch.bfloat16) * 0.1)(D, N) * 3.14),
            "C_real": _w((lambda *s: torch.randn(*s, dtype=torch.bfloat16) * 0.4)(D, N) / N ** 0.5),
            "C_imag": _w((lambda *s: torch.randn(*s, dtype=torch.bfloat16) * 0.4)(D, N) / N ** 0.5),
            "log_dt": _w((lambda *s: torch.randn(*s, dtype=torch.bfloat16) * 0.1)(D) * 0.5 - 4.0),
            "D_skip": _w((lambda *s: torch.randn(*s, dtype=torch.bfloat16) * 0.1)(D)),
        }
    _B_in = _B_setup()

    return {
        "A_x": _A_in["x"],
        "A_wqkv": _A_in["wqkv"],
        "A_wo": _A_in["wo"],
        "B_u": _B_in["u"],
        "B_log_A_real": _B_in["log_A_real"],
        "B_A_imag": _B_in["A_imag"],
        "B_C_real": _B_in["C_real"],
        "B_C_imag": _B_in["C_imag"],
        "B_log_dt": _B_in["log_dt"],
        "B_D_skip": _B_in["D_skip"],
    }

def reference(A_x, A_wqkv, A_wo, B_u, B_log_A_real, B_A_imag, B_C_real, B_C_imag, B_log_dt, B_D_skip):
    def _A_ref(x, wqkv, wo):
        B, S, D = x.shape
        H = 32; Dh = D // H
        W, dil = 8, 2
        qkv = (lambda x, *d: x.permute(*d))((x @ wqkv).reshape(B, S, 3, H, Dh), 2, 0, 3, 1, 4)
        q, k, v = qkv[0], qkv[1], qkv[2]
        scale = Dh ** -0.5
        pos = torch.arange(S)
        off = torch.arange(W) * dil
        idx = pos[:, None] - off[None, :]
        mask = idx >= 0
        idx_c = torch.where(mask, idx, 0).reshape(-1)
        kg = k[:, :, idx_c, :].reshape(B, H, S, W, Dh)
        vg = v[:, :, idx_c, :].reshape(B, H, S, W, Dh)
        logits = torch.einsum("bhsd,bhswd->bhsw", q, kg) * scale
        logits = torch.where(mask[None, None, :, :], logits, -1e9)
        attn = _softmax(logits, axis=-1)
        o = torch.einsum("bhsw,bhswd->bhsd", attn, vg)
        return (lambda x, *d: x.permute(*d))(o, 0, 2, 1, 3).reshape(B, S, D) @ wo

    def _B_ref(u, log_A_real, A_imag, C_real, C_imag, log_dt, D_skip):
        L = u.shape[1]
        dt = torch.exp(log_dt)
        A = -torch.exp(log_A_real) + 1j * A_imag
        C = (C_real + 1j * C_imag) * dt[:, None]
        pos = (lambda x, dt: x.to(dt))(torch.arange(L), log_dt.dtype)
        P = torch.exp((A * dt[:, None])[:, :, None] * pos[None, None, :])
        K = 2.0 * torch.einsum("dn,dnl->dl", C, P).real
        L2 = 2 * L
        u_t = (lambda x, *d: x.permute(*d))(u, 0, 2, 1)
        Kf = (lambda x, *a, **k: torch.fft.rfft(x.float(), *a, **k))(K, L2)
        Uf = (lambda x, *a, **k: torch.fft.rfft(x.float(), *a, **k))(u_t, L2)
        y = (lambda x, *a, **k: torch.fft.irfft(x, *a, **k).to(torch.bfloat16))(Uf * Kf[None, :, :], L2)[:, :, :L]
        y = (lambda x, *d: x.permute(*d))(y, 0, 2, 1)
        return y + u * D_skip[None, None, :]

    x = A_x
    x = x + _A_ref(_layernorm(x, axis=-1), A_wqkv, A_wo)
    x = x + _B_ref(_layernorm(x, axis=-1), B_log_A_real, B_A_imag, B_C_real, B_C_imag, B_log_dt, B_D_skip)
    x = x + _A_ref(_layernorm(x, axis=-1), A_wqkv, A_wo)
    x = x + _B_ref(_layernorm(x, axis=-1), B_log_A_real, B_A_imag, B_C_real, B_C_imag, B_log_dt, B_D_skip)
    return x
```

```cpp
#include <cuda_runtime.h>
#include <cuda_bf16.h>
#include <stdint.h>
#include <cuda.h>

typedef __nv_bfloat16 bf16;

constexpr int SEQ = 2048;
constexpr int DM = 640;
constexpr int NMODE = 192;

__device__ __forceinline__ float bf2f(bf16 v) { return __bfloat162float(v); }
__device__ __forceinline__ float rbf(float v) {
    uint32_t r;
    asm("cvt.rn.bf16x2.f32 %0, %1, %2;" : "=r"(r) : "f"(v), "f"(0.f));
    return __uint_as_float(r);
}
__device__ __forceinline__ uint32_t pack2(float lo, float hi) {
    __nv_bfloat162 t = __floats2bfloat162_rn(lo, hi);
    return *reinterpret_cast<uint32_t*>(&t);
}
__device__ __forceinline__ void pdl_sync() {
    asm volatile("griddepcontrol.wait;" ::: "memory");
    asm volatile("griddepcontrol.launch_dependents;" ::: "memory");
}
__device__ __forceinline__ uint32_t smem_u32(const void* p) { return (uint32_t)__cvta_generic_to_shared(p); }

constexpr int TPAD = 16;
constexpr int DLEN = 544;
constexpr int TAP_W2 = DLEN * 8, TAP_W3 = TAP_W2 + 768, TAP_C = TAP_W3 + 768, TAPB = TAP_C + 384;
__device__ uint4 g_tap[DM * TAPB / 16];
#define XPAD 64
constexpr int XCP = SEQ + XPAD;
__device__ __align__(128) bf16 g_x1T[DM * XCP];
__device__ __align__(128) bf16 g_xcT[DM * XCP];
__device__ __align__(128) bf16 g_o[SEQ * DM];
constexpr int WQ_STAGE = 240 * 128, WO_STAGE = 80 * 128;
__device__ __align__(128) uint4 g_wq[8 * 10 * WQ_STAGE / 16];
__device__ __align__(128) uint4 g_wo[8 * 10 * WO_STAGE / 16];
__device__ __align__(16) float g_csp[10 * 1920];
__device__ __align__(16) float2 g_sum[2 * SEQ];
__device__ __align__(16) bf16 g_piv[2 * SEQ];
__device__ uint32_t g_cflag[128], g_done;
__device__ uint32_t g_epoch;
__device__ __align__(16) unsigned long long g_rstat[SEQ];
__device__ ulonglong2 g_part[16 * 8 * 128];
__device__ ulonglong2 g_halo[2 * 16 * 8 * 640];
__device__ __forceinline__ unsigned long long tagw(uint32_t payload, uint32_t tag) { return ((unsigned long long)tag << 32) | payload; }
__device__ __forceinline__ void st_tag2(ulonglong2* p, uint32_t a, uint32_t b, uint32_t tag) {
    asm volatile("st.global.cg.v2.u64 [%0], {%1, %2};" ::"l"(p), "l"(tagw(a, tag)), "l"(tagw(b, tag)) : "memory");
}
__device__ __forceinline__ ulonglong2 ld_tag2(const ulonglong2* p) {
    ulonglong2 v;
    asm volatile("ld.relaxed.gpu.global.v2.u64 {%0, %1}, [%2];" : "=l"(v.x), "=l"(v.y) : "l"(p) : "memory");
    return v;
}
__device__ __forceinline__ bool tag_ok(ulonglong2 v, uint32_t tag) { return (uint32_t)(v.x >> 32) == tag && (uint32_t)(v.y >> 32) == tag; }
__device__ __forceinline__ uint32_t ld_epoch() { uint32_t v; asm volatile("ld.relaxed.gpu.global.u32 %0, [%1];" : "=r"(v) : "l"(&g_epoch) : "memory"); return v + 1; }
constexpr int SPIN_MAX = 1 << 20;
__device__ uint32_t g_started[4];
__device__ __forceinline__ int sm_tile(int slot) {
    if (gridDim.x == 128) return blockIdx.x;
    uint32_t s;
    asm volatile("mov.u32 %0, %smid;" : "=r"(s));
    const int h = ((int)s - 64) >> 1;
    const int tile = s < 64 ? ((s >> 1) & 7) * 16 + (s >> 4) * 2 + (s & 1) : s < 120 ? (1 + h % 7) * 16 + 8 + (h / 7) * 2 + (s & 1) : s < 124 || s > 131 ? 128 : s - 116;
    if (threadIdx.x == 0) {
        asm volatile("red.relaxed.gpu.global.add.u32 [%0], 1;" ::"l"(g_started + slot) : "memory");
        if (tile >= 128) {
            const uint32_t want = ld_epoch() * gridDim.x;
            pdl_sync();
            for (int it = 0; it < SPIN_MAX; it++) {
                uint32_t v;
                asm volatile("ld.relaxed.gpu.global.u32 %0, [%1];" : "=r"(v) : "l"(g_started + slot) : "memory");
                if ((int)(v - want) >= 0) break;
                __nanosleep(100);
            }
        }
    }
    return tile;
}
#define DBG_SYMS
#define TSTAMP(i)
#define TSTAMP1(i)
#define TSTAMP1T(i, t)
#define TSTAMP1X(i, t)
#define SPAN(k, i)
#define GSTAMP(arr, i)
#define TSTAMP2(i)
#define TSTAMP3(i)
#define TSTAMP4(i)
#define TSTAMPK(i, t)

__device__ __forceinline__ float2 cexp_at(float wr2, float wi, float p) {
    float er;
    asm("ex2.approx.ftz.f32 %0, %1;" : "=f"(er) : "f"(wr2 * p));
    float th = wi * p;
    const float k = rintf(th * 0.15915494309189535f);
    th = fmaf(k, -6.2831854820251465f, th);
    th = fmaf(k, 1.7484555314695172e-7f, th);
    return make_float2(er * __cosf(th), er * __sinf(th));
}
__device__ __forceinline__ float2 cmul(float2 a, float2 b) {
    return make_float2(fmaf(a.x, b.x, -a.y * b.y), fmaf(a.x, b.y, a.y * b.x));
}
__device__ __forceinline__ float2 csqr(float2 a) { return make_float2(fmaf(a.x, a.x, -a.y * a.y), (a.x + a.x) * a.y); }
__device__ __forceinline__ uint32_t packh(float2 v) {
    uint32_t r;
    asm("cvt.rn.f16x2.f32 %0, %1, %2;" : "=r"(r) : "f"(v.y), "f"(v.x));
    return r;
}
__device__ __forceinline__ void mma_f16(float* d, uint32_t a0, uint32_t a1, uint32_t a2, uint32_t a3, uint32_t b0, uint32_t b1) {
    asm volatile("mma.sync.aligned.m16n8k16.row.col.f32.f16.f16.f32 {%0,%1,%2,%3}, {%4,%5,%6,%7}, {%8,%9}, {%0,%1,%2,%3};"
                 : "+f"(d[0]), "+f"(d[1]), "+f"(d[2]), "+f"(d[3]) : "r"(a0), "r"(a1), "r"(a2), "r"(a3), "r"(b0), "r"(b1));
}

struct KgIn { const bf16 *logA, *Aim, *Cre, *Cim, *logdt, *x, *wqkv, *wo; };
constexpr int KG_THREADS = NMODE / 2;

__global__ void __launch_bounds__(KG_THREADS, 5) kgen_kernel(const KgIn in) {
    __shared__ __align__(128) uint4 tab[3 * 896];
    __shared__ __align__(16) unsigned short E[1024];
    const int d = blockIdx.x, tid = threadIdx.x, lane = tid & 31, warp = tid >> 5;
    SPAN(0, 0); SPAN(0, 1);
    TSTAMPK(0, 0);
    asm volatile("griddepcontrol.launch_dependents;" ::: "memory");
    const bf16 pdt = in.logdt[d];
    const uint32_t pla = reinterpret_cast<const uint32_t*>(in.logA)[d * KG_THREADS + tid], pai = reinterpret_cast<const uint32_t*>(in.Aim)[d * KG_THREADS + tid];
    const uint32_t pcr = reinterpret_cast<const uint32_t*>(in.Cre)[d * KG_THREADS + tid], pci = reinterpret_cast<const uint32_t*>(in.Cim)[d * KG_THREADS + tid];
    const bf16* pfq = tid < 30 ? in.wqkv + (size_t)(d * 30 + tid) * 64 : tid < 40 ? in.wo + (size_t)(d * 10 + tid - 30) * 64 : in.x + (size_t)(d * 32 + tid - 40) * 64;
    if (tid < 72) asm volatile("prefetch.global.L2 [%0];" ::"l"(pfq));
    reinterpret_cast<uint4*>(E)[tid] = make_uint4(0, 0, 0, 0);
    if (tid < 32) reinterpret_cast<uint4*>(E)[96 + tid] = make_uint4(0, 0, 0, 0);
    const uint32_t tw = smem_u32(tab) + warp * 14336;
    const int g = lane >> 2, t = lane & 3;
    const uint32_t sta = tw + lane * 128 + ((2 * (lane & 3) + ((lane >> 2) & 1)) << 4);
    const uint32_t lda = tw + t * 128 + ((g ^ (2 * t)) << 4);
    const uint32_t stb = tw + 12288 + lane * 64 + ((4 * ((lane >> 1) & 1) + ((lane >> 2) & 3)) << 3);
    const uint32_t ldb = tw + 12288 + t * 64 + ((g ^ (4 * (t >> 1))) << 3);
    auto sts4 = [&](int e, int off, uint32_t a, uint32_t b, uint32_t c, uint32_t dd) {
        asm volatile("st.shared.v4.u32 [%0], {%1,%2,%3,%4};" ::"r"((sta ^ (e << 4)) + off), "r"(a), "r"(b), "r"(c), "r"(dd) : "memory");
    };
    auto lds4 = [&](int sp, int off, uint32_t* r) {
        asm volatile("ld.shared.v4.u32 {%0,%1,%2,%3}, [%4];" : "=r"(r[0]), "=r"(r[1]), "=r"(r[2]), "=r"(r[3]) : "r"((lda ^ ((sp & 1) << 4)) + sp * 512 + off) : "memory");
    };
    const float dt = rbf(expf(bf2f(pdt)));
    float2 C[2], y1[2], z8[2], y128[2];
    float cmax = 0.f;
#pragma unroll
    for (int m = 0; m < 2; m++) {
        const float wr2 = -rbf(expf(__uint_as_float(m ? pla & 0xffff0000u : pla << 16))) * dt * 1.4426950408889634f;
        const float wi = __uint_as_float(m ? pai & 0xffff0000u : pai << 16) * dt;
        C[m] = make_float2(__uint_as_float(m ? pcr & 0xffff0000u : pcr << 16) * dt, -__uint_as_float(m ? pci & 0xffff0000u : pci << 16) * dt);
        cmax = fmaxf(cmax, fmaxf(fabsf(C[m].x), fabsf(C[m].y)));
        y1[m] = cexp_at(wr2, -wi, 1.f); z8[m] = cexp_at(wr2, wi, 8.f); y128[m] = cexp_at(wr2, -wi, 128.f);
    }
    const int ex = min(max((int)(__reduce_max_sync(~0u, __float_as_uint(cmax)) >> 23), 20), 240);
    const float scale = __uint_as_float((uint32_t)(127 + 10 + 127 - ex) << 23), unscale = 2.0f * __uint_as_float((uint32_t)(ex - 10) << 23);
    TSTAMPK(4, 0);
    float k2048 = 0.f;
    {
        float2 h0[2], h1[2], g0[2], g1[2], g2[2], g2b[2], g3[2], g4[2], y2[2], y4[2];
#pragma unroll
        for (int m = 0; m < 2; m++) {
            h0[m] = make_float2(1.f, 0.f); h1[m] = csqr(csqr(csqr(z8[m])));
            g0[m] = make_float2(C[m].x * scale, C[m].y * scale);
            g1[m] = cmul(g0[m], y128[m]);
            const float2 y256 = csqr(y128[m]), y512 = csqr(y256);
            g2b[m] = g2[m] = cmul(g0[m], y256); g3[m] = cmul(g0[m], y512); g4[m] = cmul(g3[m], y512);
            y2[m] = csqr(y1[m]); y4[m] = csqr(y2[m]);
        }
#pragma unroll
        for (int e = 0; e < 8; e++) {
            sts4(e, 0, packh(h0[0]), packh(h1[0]), packh(h0[1]), packh(h1[1]));
            sts4(e, 4096, packh(g0[0]), packh(g0[1]), packh(g1[0]), packh(g1[1]));
            sts4(e, 8192, packh(g2[0]), packh(g2[1]), packh((e & 1) ? cmul(g3[0], y4[0]) : g3[0]), packh((e & 1) ? cmul(g3[1], y4[1]) : g3[1]));
            asm volatile("st.shared.v2.u32 [%0], {%1,%2};" ::"r"(stb ^ (e << 3)), "r"(packh(g4[0])), "r"(packh(g4[1])) : "memory");
#pragma unroll
            for (int m = 0; m < 2; m++) {
                if (e < 7) {
                    h0[m] = e ? cmul(h0[m], z8[m]) : z8[m]; h1[m] = cmul(h1[m], z8[m]); g0[m] = cmul(g0[m], y1[m]); g1[m] = cmul(g1[m], y1[m]);
                    g2[m] = e == 3 ? cmul(g2b[m], y128[m]) : cmul(g2[m], y2[m]);
                    if (e & 1) g3[m] = cmul(g3[m], y128[m]);
                    g4[m] = cmul(g4[m], y128[m]);
                } else k2048 += fmaf(g4[m].x, y128[m].x, -g4[m].y * y128[m].y);
            }
        }
    }
    TSTAMPK(6, 0);
    const int job = warp * DM + d;
    const bool isq = job < 1200;
    uint32_t sw[16];
    unsigned char* sdst = nullptr;
    int sn = 0;
    if (job < 1600) {
        const int j2 = isq ? job : job - 1200, kb = j2 % 10, col = (j2 / 10) * 16 + (lane >> 3) * 4;
        if (isq) {
            const int sec = col / DM, r = col - sec * DM, hg = r / 80;
            sn = hg * 160 + sec * 80 + r;
            sdst = reinterpret_cast<unsigned char*>(g_wq) + (hg * 9 + kb) * WQ_STAGE;
        } else {
            sn = col;
            sdst = reinterpret_cast<unsigned char*>(g_wo) + ((col / 80) * 9 + kb) * WO_STAGE;
        }
        const int pitch = isq ? 3 * DM : DM;
        const bf16* src = (isq ? in.wqkv : in.wo) + (size_t)(kb * 64 + (lane & 7) * 8) * pitch + col;
#pragma unroll
        for (int i = 0; i < 8; i++) {
            const uint2 v = __ldg(reinterpret_cast<const uint2*>(src + i * pitch));
            sw[2 * i] = v.x; sw[2 * i + 1] = v.y;
        }
        sn += kb << 16;
    } else if (job < 1600 + 64) {
        reinterpret_cast<uint4*>(g_sum)[(job - 1600) * 32 + lane] = make_uint4(0, 0, 0, 0);
    }
    __syncwarp();
    float acc[5][4];
#pragma unroll
    for (int j = 0; j < 5; j++)
#pragma unroll
        for (int k = 0; k < 4; k++) acc[j][k] = 0.f;
#pragma unroll
    for (int sp = 0; sp < 8; sp++) {
        uint32_t a[4], b[4], c[4], e0, e1;
        lds4(sp, 0, a); lds4(sp, 4096, b); lds4(sp, 8192, c);
        asm volatile("ld.shared.v2.u32 {%0,%1}, [%2];" : "=r"(e0), "=r"(e1) : "r"((ldb ^ ((sp & 3) << 3)) + sp * 256) : "memory");
        mma_f16(acc[0], a[0], a[1], a[2], a[3], b[0], b[1]);
        mma_f16(acc[1], a[0], a[1], a[2], a[3], b[2], b[3]);
        mma_f16(acc[2], a[0], a[1], a[2], a[3], c[0], c[1]);
        mma_f16(acc[3], a[0], a[1], a[2], a[3], c[2], c[3]);
        mma_f16(acc[4], a[0], a[1], a[2], a[3], e0, e1);
    }
#pragma unroll
    for (int o = 16; o; o >>= 1) k2048 += __shfl_xor_sync(~0u, k2048, o);
    __syncwarp();
    {
        float* Pp = reinterpret_cast<float*>(tab + warp * 896);
#pragma unroll
        for (int h = 0; h < 2; h++) {
            const int b = g + 8 * h;
            *reinterpret_cast<float2*>(Pp + 8 * b + 2 * t) = make_float2(acc[0][2 * h] * unscale, acc[0][2 * h + 1] * unscale);
            *reinterpret_cast<float2*>(Pp + 128 + 8 * b + 2 * t) = make_float2(acc[1][2 * h] * unscale, acc[1][2 * h + 1] * unscale);
            *reinterpret_cast<float2*>(Pp + 256 + 4 * b + 2 * (t & 1) + 64 * (t >> 1)) = make_float2(acc[2][2 * h] * unscale, acc[2][2 * h + 1] * unscale);
            *reinterpret_cast<float2*>(Pp + 384 + 2 * b + 32 * t) = make_float2(acc[3][2 * h] * unscale, acc[3][2 * h + 1] * unscale);
            Pp[512 + b + 32 * t] = acc[4][2 * h] * unscale;
            Pp[512 + b + 32 * t + 16] = acc[4][2 * h + 1] * unscale;
        }
        if (lane == 0) Pp[640] = k2048 * unscale;
    }
    TSTAMPK(7, 0);
    __syncthreads();
    TSTAMPK(9, 0);
    const float* Kp = reinterpret_cast<const float*>(tab);
    auto ksum = [&](int i) -> float { return (Kp[i] + Kp[3584 + i]) + Kp[7168 + i]; };
    auto ksum4 = [&](int q) -> float4 {
        const float4 a = reinterpret_cast<const float4*>(Kp)[q], b = reinterpret_cast<const float4*>(Kp)[896 + q], c = reinterpret_cast<const float4*>(Kp)[1792 + q];
        return make_float4((a.x + b.x) + c.x, (a.y + b.y) + c.y, (a.z + b.z) + c.z, (a.w + b.w) + c.w);
    };
    uint32_t* E2w = reinterpret_cast<uint32_t*>(E);
    {
        float4 v = ksum4(tid);
        if (tid == 95) v.w -= rbf(ksum(384));
        const uint32_t lo = pack2(v.x, v.y), hi = pack2(v.z, v.w);
        if (tid < 64) { E2w[9 + 2 * tid] = lo; E2w[10 + 2 * tid] = hi; }
        else {
            const int l = 256 + 8 * (tid - 64);
            if (tid > 64) E[18 + l - 1] = (unsigned short)lo;
            E2w[9 + l / 2] = __byte_perm(lo, 0, 0x1010);
            E2w[10 + l / 2] = __byte_perm(lo, hi, 0x5432);
            E2w[11 + l / 2] = __byte_perm(hi, 0, 0x1010);
            E[18 + l + 6] = (unsigned short)(hi >> 16);
        }
    }
    unsigned char* out = reinterpret_cast<unsigned char*>(g_tap) + (size_t)d * TAPB;
    if (tid < 64) {
        float4 v = ksum4(96 + tid);
        if (tid == 31) v.w -= rbf(ksum(512));
        const int o = (tid < 32 ? 317 : 417 - 64) + 2 * tid;
        E2w[o] = pack2(v.x, v.y); E2w[o + 1] = pack2(v.z, v.w);
    } else if (tid < 88) {
        const int x = 992 + 2 * (tid - 64);
        const uint32_t kc = __float_as_uint(rbf(ksum(512))) >> 16;
        auto wc = [&](int xx) -> uint32_t { return xx == 1019 ? kc : xx == 1020 ? kc << 16 : 0u; };
        reinterpret_cast<uint4*>(out + TAP_C)[tid - 64] = make_uint4(wc(x), wc(x + 8), wc(x + 1), wc(x + 9));
    } else if (tid == 88) E[800 + 34 + 128] = (unsigned short)(__float_as_uint(rbf(ksum(640))) >> 16);
    if (job < 1600) {
        const int c = lane & 7, n = sn & 0xffff;
#pragma unroll
        for (int q = 0; q < 4; q++) {
            uint32_t w[4];
#pragma unroll
            for (int j = 0; j < 4; j++) w[j] = __byte_perm(sw[4 * j + (q >> 1)], sw[4 * j + 2 + (q >> 1)], (q & 1) ? 0x7632 : 0x5410);
            *reinterpret_cast<uint4*>(sdst + (n + q) * 128 + ((c ^ ((n + q) & 7)) << 4)) = make_uint4(w[0], w[1], w[2], w[3]);
        }
    }
    __syncthreads();
    const uint32_t* E2 = reinterpret_cast<const uint32_t*>(E);
#pragma unroll
    for (int k = 0; k < 3; k++) {
        const int i = tid + KG_THREADS * k;
        if (i < DLEN / 2) {
            const uint32_t w0 = E2[i], w1 = E2[i + 1], w4 = E2[i + 4], w5 = E2[i + 5];
            reinterpret_cast<uint4*>(out)[i] = make_uint4(__byte_perm(w1, w0, 0x7610), __byte_perm(w5, w4, 0x7610), __byte_perm(w1, w1, 0x1032), __byte_perm(w5, w5, 0x1032));
        }
    }
    {
        const uint32_t a0 = E2[300 + tid], a1 = E2[301 + tid], b0 = E2[400 + tid], b1 = E2[401 + tid];
        reinterpret_cast<uint2*>(out + TAP_W2)[tid] = make_uint2(__byte_perm(a1, a0, 0x7610), __byte_perm(a1, a1, 0x1032));
        reinterpret_cast<uint2*>(out + TAP_W3)[tid] = make_uint2(__byte_perm(b1, b0, 0x7610), __byte_perm(b1, b1, 0x1032));
    }
    TSTAMPK(10, 0);
    if (isq) {
        float4 a = make_float4(0.f, 0.f, 0.f, 0.f);
#pragma unroll
        for (int i = 0; i < 8; i++) {
            a.x += __uint_as_float(sw[2 * i] << 16); a.y += __uint_as_float(sw[2 * i] & 0xffff0000u);
            a.z += __uint_as_float(sw[2 * i + 1] << 16); a.w += __uint_as_float(sw[2 * i + 1] & 0xffff0000u);
        }
#pragma unroll
        for (int o = 1; o <= 4; o <<= 1) {
            a.x += __shfl_xor_sync(~0u, a.x, o); a.y += __shfl_xor_sync(~0u, a.y, o);
            a.z += __shfl_xor_sync(~0u, a.z, o); a.w += __shfl_xor_sync(~0u, a.w, o);
        }
        if ((lane & 7) == 0) *reinterpret_cast<float4*>(g_csp + (sn >> 16) * 1920 + (sn & 0xffff)) = a;
    }
    TSTAMPK(11, 0);
    SPAN(0, 3);
}

constexpr int CV_CPB = 5;
constexpr int CV_THREADS = 512;
constexpr int UPADF = 128;
constexpr int ULEN = UPADF + SEQ + 80;
constexpr int XLEN = SEQ + 16;
constexpr int BX_5 = 0, BX_3 = 3264, BX_9 = 6528, BX_7 = 8960, BX_LEN = 11392;
constexpr int CV_SM_T = 0;
constexpr int CV_SM_B = CV_CPB * TAPB;
constexpr int CV_SM_U = CV_SM_B + CV_CPB * BX_LEN;
constexpr int CV_SM_X = CV_SM_U + CV_CPB * ULEN * 2;
constexpr int CV_SM_Y = CV_SM_X + CV_CPB * XLEN * 2;
constexpr int CV_SM_P = CV_SM_Y + CV_CPB * XLEN * 2;
constexpr int CV_SM_CNT = CV_SM_P + 6 * 4096;
constexpr int CV_SMEM = CV_SM_CNT + 128;
static_assert(CV_SM_B % 128 == 0 && CV_SM_CNT % 16 == 0, "layout");

__device__ __forceinline__ void mma_bf16(float* d, uint32_t a0, uint32_t a1, uint32_t a2, uint32_t a3, uint32_t b0, uint32_t b1) {
    asm volatile("mma.sync.aligned.m16n8k16.row.col.f32.bf16.bf16.f32 {%0,%1,%2,%3}, {%4,%5,%6,%7}, {%8,%9}, {%0,%1,%2,%3};"
                 : "+f"(d[0]), "+f"(d[1]), "+f"(d[2]), "+f"(d[3]) : "r"(a0), "r"(a1), "r"(a2), "r"(a3), "r"(b0), "r"(b1));
}
__device__ __forceinline__ void mma_bf16_k8(float* d, uint32_t a0, uint32_t a1, uint32_t b0) {
    asm volatile("mma.sync.aligned.m16n8k8.row.col.f32.bf16.bf16.f32 {%0,%1,%2,%3}, {%4,%5}, {%6}, {%0,%1,%2,%3};"
                 : "+f"(d[0]), "+f"(d[1]), "+f"(d[2]), "+f"(d[3]) : "r"(a0), "r"(a1), "r"(b0));
}
__device__ __forceinline__ void ldsm_x4(uint32_t* r, uint32_t addr) {
    asm volatile("ldmatrix.sync.aligned.m8n8.x4.shared.b16 {%0,%1,%2,%3}, [%4];"
                 : "=r"(r[0]), "=r"(r[1]), "=r"(r[2]), "=r"(r[3]) : "r"(addr));
}

__device__ __forceinline__ void ldsm_x4_t(uint32_t* r, uint32_t addr) {
    asm volatile("ldmatrix.sync.aligned.m8n8.x4.trans.shared.b16 {%0,%1,%2,%3}, [%4];"
                 : "=r"(r[0]), "=r"(r[1]), "=r"(r[2]), "=r"(r[3]) : "r"(addr));
}
__device__ __forceinline__ uint32_t ln2(uint32_t x, uint32_t m, float ra, float rb) {
    const __nv_bfloat162 d = __hsub2(*reinterpret_cast<const __nv_bfloat162*>(&x), *reinterpret_cast<const __nv_bfloat162*>(&m));
    const uint32_t w = *reinterpret_cast<const uint32_t*>(&d);
    return pack2(__uint_as_float(w << 16) * ra, __uint_as_float(w & 0xffff0000u) * rb);
}
__device__ __forceinline__ void cp_async16(uint32_t dst, const void* src) {
    asm volatile("cp.async.cg.shared.global [%0], [%1], 16;" ::"r"(dst), "l"(src));
}
__device__ __forceinline__ void cp_async_wait_all() { asm volatile("cp.async.wait_all;" ::: "memory"); }

template <bool FULL>
__device__ __forceinline__ void direct_pass(float (&acc)[8][4], uint32_t ub, uint32_t o0, uint32_t o1, const uint2* __restrict__ Tp, bool first_half) {
    uint32_t sw[8][8];
#pragma unroll
    for (int j = 0; j < 8; j++) { ldsm_x4(&sw[j][0], ub + o0 + j * 256); ldsm_x4(&sw[j][4], ub + o1 + j * 256); }
#pragma unroll
    for (int M = 0; M < 4; M++) {
#pragma unroll
        for (int i = 0; i < 4; i++) {
            const uint2 hi = Tp[128 * M + 16 * i], lo = Tp[128 * M + 16 * i - 8];
#pragma unroll
            for (int j = FULL ? 0 : M; j < 8; j++) mma_bf16(acc[j], hi.x, hi.y, lo.x, lo.y, sw[(j - M) & 7][2 * i], sw[(j - M) & 7][2 * i + 1]);
        }
        if (FULL) {
            ldsm_x4(&sw[7 - M][0], ub + o0 - (M + 1) * 256);
            if (M < 3) ldsm_x4(&sw[7 - M][4], ub + o1 - (M + 1) * 256);
        }
    }
    if (first_half) {
        const uint2 hi = Tp[512], lo = Tp[504];
#pragma unroll
        for (int j = FULL ? 0 : 4; j < 8; j++) mma_bf16(acc[j], hi.x, hi.y, lo.x, lo.y, sw[(j - 4) & 7][0], sw[(j - 4) & 7][1]);
    }
}
__device__ __forceinline__ void mbar_init(uint32_t bar, int count) { asm volatile("mbarrier.init.shared::cta.b64 [%0], %1;" ::"r"(bar), "r"(count)); }
__device__ __forceinline__ void mbar_arrive(uint32_t bar) { asm volatile("mbarrier.arrive.shared::cta.b64 _, [%0];" ::"r"(bar) : "memory"); }
__device__ __forceinline__ void mbar_wait(uint32_t bar, uint32_t parity) {
    asm volatile("{\n.reg .pred p;\nWAIT_LOOP:\n"
                 "mbarrier.try_wait.parity.shared::cta.b64 p, [%0], %1;\n"
                 "@p bra.uni WAIT_DONE;\nbra.uni WAIT_LOOP;\nWAIT_DONE:\n}" ::"r"(bar), "r"(parity) : "memory");
}

__device__ __forceinline__ uint32_t fin2(uint32_t x, uint32_t y, uint32_t u, uint32_t dk) {
    typedef __nv_bfloat162 b2;
    const b2 r = __hadd2_rn(*reinterpret_cast<const b2*>(&x), __hadd2_rn(*reinterpret_cast<const b2*>(&y),
                            __hmul2_rn(*reinterpret_cast<const b2*>(&u), *reinterpret_cast<const b2*>(&dk))));
    return *reinterpret_cast<const uint32_t*>(&r);
}
__global__ void __launch_bounds__(CV_THREADS, 1) conv_kernel(const bf16* __restrict__ Dskip, int layer, bf16* __restrict__ xout) {
    extern __shared__ __align__(128) unsigned char sm[];
    SPAN(3 + 4 * layer, 0);
    bf16* Us = reinterpret_cast<bf16*>(sm + CV_SM_U);
    bf16* Xs = reinterpret_cast<bf16*>(sm + CV_SM_X);
    bf16* Ys = reinterpret_cast<bf16*>(sm + CV_SM_Y);
    const int tid = threadIdx.x, lane = tid & 31, warp = tid >> 5;
    const int d0 = blockIdx.x * CV_CPB, tile = blockIdx.x; (void)tile;
    if (tid >= 256) {
        const uint4* src = g_tap + (size_t)d0 * (TAPB / 16);
        for (int i = tid - 256; i < CV_CPB * TAPB / 16; i += 256) cp_async16(smem_u32(sm + CV_SM_T) + i * 16, src + i);
        asm volatile("cp.async.commit_group;" ::: "memory");
        if (tid < 256 + 13) mbar_init(smem_u32(sm + CV_SM_CNT) + 8 * (tid - 256), tid < 256 + 12 ? 1 : 16);
        for (int i = tid - 256; i < CV_CPB * 149; i += 256) {
            const int c = i / 149, k = i - c * 149;
            unsigned char* bx = sm + CV_SM_B + c * BX_LEN;
            unsigned char* us = sm + CV_SM_U + c * ULEN * 2;
            unsigned char* dst = k < 18 ? bx + BX_5 + 8 * k : k < 37 ? bx + BX_3 + 8 * (k - 18) : k < 69 ? bx + BX_9 + 8 * (k - 37)
                               : k < 101 ? bx + BX_7 + 8 * (k - 69) : k < 133 ? us + 8 * (k - 101) : us + (UPADF + SEQ) * 2 + 8 * (k - 133);
            *reinterpret_cast<uint2*>(dst) = make_uint2(0, 0);
        }
    }
    pdl_sync();
    SPAN(3 + 4 * layer, 1);
    TSTAMP(0);
    if (threadIdx.x == 0) { GSTAMP(g_tim, 15); }
    if (tid < 256) {
        const uint4 pv = __ldcg(reinterpret_cast<const uint4*>(g_piv + layer * SEQ) + tid);
        float4 sv[4];
#pragma unroll
        for (int k = 0; k < 4; k++) sv[k] = __ldcg(reinterpret_cast<const float4*>(g_sum + layer * SEQ) + 256 * k + tid);
        uint4 xv[CV_CPB];
#pragma unroll
        for (int c = 0; c < CV_CPB; c++) xv[c] = __ldcg(reinterpret_cast<const uint4*>(g_x1T + (size_t)(d0 + c) * XCP) + tid);
        uint32_t mw[4];
        float rs[8];
#pragma unroll
        for (int k = 0; k < 4; k++) {
            const uint32_t pw = k == 0 ? pv.x : k == 1 ? pv.y : k == 2 ? pv.z : pv.w;
            const float d0_ = sv[k].x * (1.0f / DM), d1_ = sv[k].z * (1.0f / DM);
            mw[k] = pack2(__uint_as_float(pw << 16) + d0_, __uint_as_float(pw & 0xffff0000u) + d1_);
            const uint32_t vr = pack2(fmaxf(fmaf(-d0_, d0_, sv[k].y * (1.0f / DM)), 0.f), fmaxf(fmaf(-d1_, d1_, sv[k].w * (1.0f / DM)), 0.f));
            const uint32_t ve = pack2(__uint_as_float(vr << 16) + 1e-5f, __uint_as_float(vr & 0xffff0000u) + 1e-5f);
            const uint32_t sd = pack2(sqrtf(__uint_as_float(ve << 16)), sqrtf(__uint_as_float(ve & 0xffff0000u)));
            rs[2 * k] = __frcp_rn(__uint_as_float(sd << 16)); rs[2 * k + 1] = __frcp_rn(__uint_as_float(sd & 0xffff0000u));
        }
        const uint4 mv = make_uint4(mw[0], mw[1], mw[2], mw[3]);
        const float4 r0 = make_float4(rs[0], rs[1], rs[2], rs[3]), r1 = make_float4(rs[4], rs[5], rs[6], rs[7]);
        const int ch = tid + UPADF / 8, pch = ch ^ ((ch >> 3) & 1);
#pragma unroll
        for (int c = 0; c < CV_CPB; c++) {
            *reinterpret_cast<uint4*>(Xs + c * XLEN + tid * 8) = xv[c];
            *reinterpret_cast<uint4*>(Us + c * ULEN + pch * 8) =
                make_uint4(ln2(xv[c].x, mv.x, r0.x, r0.y), ln2(xv[c].y, mv.y, r0.z, r0.w), ln2(xv[c].z, mv.z, r1.x, r1.y), ln2(xv[c].w, mv.w, r1.z, r1.w));
        }
    }
    const uint32_t dskl = (uint32_t)__bfloat16_as_ushort(Dskip[d0 + min(lane, CV_CPB - 1)]) * 0x10001u;
    const uint32_t tag = ld_epoch();
    cp_async_wait_all();
    __syncthreads();
    TSTAMP(1);
    const uint32_t rstart = warp < 8 ? (warp < 4 ? 0x02000000u : 0x06040000u) : (warp < 12 ? 0x0C0B0A08u : 0x1E1D150Fu);
    const uint32_t rcount = warp < 8 ? 0x02020000u : (warp < 12 ? 0x03010102u : 0x01010806u);
#pragma unroll 1
    for (int rd = (rstart >> (8 * (warp & 3))) & 0xff, re = rd + ((rcount >> (8 * (warp & 3))) & 0xff); rd < re; rd++) {
        const int i = 32 * rd + lane;
        if (i < CV_CPB * 193) {
            const int c = i / 193, chunk = i - c * 193 - 1, ch = chunk + UPADF / 8;
            const bf16* uc = Us + c * ULEN;
            const uint4 o = *reinterpret_cast<const uint4*>(uc + (ch ^ ((ch >> 3) & 1)) * 8);
            const uint2 lo = *reinterpret_cast<const uint2*>(uc + ((ch - 1) ^ (((ch - 1) >> 3) & 1)) * 8 + 4);
            const uint2 hi = *reinterpret_cast<const uint2*>(uc + ((ch + 1) ^ (((ch + 1) >> 3) & 1)) * 8);
            const uint32_t w[8] = {lo.x, lo.y, o.x, o.y, o.z, o.w, hi.x, hi.y};
            float v[16], b[8];
#pragma unroll
            for (int k = 0; k < 8; k++) { v[2 * k] = __uint_as_float(w[k] << 16); v[2 * k + 1] = __uint_as_float(w[k] & 0xffff0000u); }
            unsigned char* bx = sm + CV_SM_B + c * BX_LEN + chunk * 16;
#pragma unroll
            for (int k = 0; k < 8; k++) b[k] = v[k + 4] + (v[k + 3] + v[k + 5]);
            *reinterpret_cast<uint2*>(bx + BX_3 + 168) = make_uint2(pack2(b[0], b[1]), pack2(b[2], b[3]));
            *reinterpret_cast<uint2*>(bx + BX_3 + 176) = make_uint2(pack2(b[4], b[5]), pack2(b[6], b[7]));
#pragma unroll
            for (int k = 0; k < 8; k++) b[k] += v[k + 2] + v[k + 6];
            *reinterpret_cast<uint4*>(bx + BX_5 + 160) = make_uint4(pack2(b[0], b[1]), pack2(b[2], b[3]), pack2(b[4], b[5]), pack2(b[6], b[7]));
            if (chunk < 128) {
#pragma unroll
                for (int k = 0; k < 8; k++) b[k] += v[k + 1] + v[k + 7];
                *reinterpret_cast<uint4*>(bx + BX_7 + 272) = make_uint4(pack2(b[0], b[1]), pack2(b[2], b[3]), pack2(b[4], b[5]), pack2(b[6], b[7]));
#pragma unroll
                for (int k = 0; k < 8; k++) b[k] += v[k] + v[k + 8];
                *reinterpret_cast<uint4*>(bx + BX_9 + 272) = make_uint4(pack2(b[0], b[1]), pack2(b[2], b[3]), pack2(b[4], b[5]), pack2(b[6], b[7]));
            }
        }
    }
    __syncwarp();
    if (lane == 0) mbar_arrive(smem_u32(sm + CV_SM_CNT) + 96);
    TSTAMP(2);
    {
        const int g = lane >> 2, ti = lane & 3;
        const int e = g - 2 * ti;
        uint32_t lds_off[4];
        uint32_t off2, off3, offc;
        {
            const int mat = lane >> 3, r = lane & 7;
#pragma unroll
            for (int pr = 0; pr < 4; pr++) {
                const int iw = 2 * pr + (mat >> 1), half = mat & 1;
                const int chunk = (UPADF - 16 * iw + 16 * r + 8 * half) >> 3;
                lds_off[pr] = (uint32_t)((chunk ^ ((chunk >> 3) & 1)) * 16);
            }
            const int j2 = 13 + r + 8 * (mat >> 1), j3 = j2 + 2, i0 = 8 * (mat & 1);
            off2 = (j2 & 1) ? BX_3 + (4 * j2 + i0 + 84) * 2 : BX_5 + (4 * j2 + i0 + 80) * 2;
            off3 = ((j3 & 1) ? BX_7 : BX_9) + (8 * j3 + i0 + 136) * 2;
            const int cc = (UPADF + 16 * (r + (mat >> 1)) + i0) >> 3;
            offc = (uint32_t)((cc ^ ((cc >> 3) & 1)) * 16);
        }
        const uint32_t rtab = warp < 8 ? (warp < 4 ? 0x0B090200u : 0x0C0A0301u) : (warp < 12 ? 0x13111008u : 0x1412241Cu);
        const int rl = (rtab >> (8 * (warp & 3))) & 0xff, type = rl >> 3, c = rl & 7;
        const int H = (type == 1 || type == 2) ? 1 : 0, T0 = 8 * H;
        const uint2* Tc = reinterpret_cast<const uint2*>(sm + CV_SM_T + c * TAPB) + TPAD + e;
        const uint32_t ubase = smem_u32(Us + c * ULEN);
        const uint32_t bbase = smem_u32(sm + CV_SM_B + c * BX_LEN);
        float acc[8][4];
#pragma unroll
        for (int j = 0; j < 8; j++)
#pragma unroll
            for (int k = 0; k < 4; k++) acc[j][k] = 0.f;
#pragma unroll 1
        for (int pass = (type == 2 || type == 4) ? 1 : 0; pass < ((type == 1 || type == 3) ? 1 : 2); pass++) {
            const uint32_t o0 = pass ? lds_off[2] : lds_off[0], o1 = pass ? lds_off[3] : lds_off[1];
            if (H) direct_pass<true>(acc, ubase + T0 * 256, o0, o1, Tc + 64 * pass, pass == 0);
            else direct_pass<false>(acc, ubase, o0, o1, Tc + 64 * pass, pass == 0);
        }
        TSTAMP(6);
        mbar_wait(smem_u32(sm + CV_SM_CNT) + 96, 0);
        if (type != 1 && type != 4) {
            const uint32_t* w2 = reinterpret_cast<const uint32_t*>(sm + CV_SM_T + c * TAPB + TAP_W2) + (115 - 96) + 4 * g - 2 * ti;
            uint32_t f[10][2];
#pragma unroll
            for (int k = 0; k < 10; k++) { f[k][0] = w2[16 * k]; f[k][1] = w2[16 * k - 8]; }
            const uint32_t ab = bbase + off2 + (2 * T0 + 6) * 128;
            const int kmax = H ? 23 : 8;
            uint32_t a[3][4];
            ldsm_x4_t(a[0], ab);
            ldsm_x4_t(a[1], ab - 128);
#pragma unroll
            for (int kp = 0; kp < 24; kp++) {
                if (kp > kmax) break;
                if (kp < 22) ldsm_x4_t(a[(kp + 2) % 3], ab - min(kp + 2, kmax) * 128);
#pragma unroll
                for (int j = 0; j < 8; j++) {
                    const int ee = 2 * j - 14 + kp;
                    if (ee >= 0 && ee <= 9) mma_bf16(acc[j], a[kp % 3][0], a[kp % 3][1], a[kp % 3][2], a[kp % 3][3], f[ee][0], f[ee][1]);
                }
            }
        }
        TSTAMP(7);
        if (type != 2 && type != 4) {
            const uint32_t* w3 = reinterpret_cast<const uint32_t*>(sm + CV_SM_T + c * TAPB + TAP_W3) + (129 - 96) + 2 * (g - ti);
            uint32_t f[9][2];
#pragma unroll
            for (int k = 0; k < 9; k++) { f[k][0] = w3[16 * k]; f[k][1] = w3[16 * k - 8]; }
            const uint32_t ab = bbase + off3 + (T0 - 2) * 256;
            uint32_t a[3][4];
            ldsm_x4_t(a[0], ab);
            ldsm_x4_t(a[1], ab - H * 256);
#pragma unroll
            for (int kp = 0; kp < 9; kp++) {
                if (kp > T0) break;
                if (kp < 7) ldsm_x4_t(a[(kp + 2) % 3], ab - min(kp + 2, T0) * 256);
#pragma unroll
                for (int j = 0; j < 8; j++) {
                    const int dl = j - 7 + kp;
                    if (dl >= 0 && dl <= 8) mma_bf16(acc[j], a[kp % 3][0], a[kp % 3][1], a[kp % 3][2], a[kp % 3][3], f[dl][0], f[dl][1]);
                }
            }
            const uint2* Dc = reinterpret_cast<const uint2*>(sm + CV_SM_T + c * TAPB + TAP_C) + e;
            const uint2 h63 = Dc[16], h64 = Dc[32], l63 = Dc[8], l64 = Dc[24];
#pragma unroll
            for (int j = 0; j < 8; j++)
                if (j == 7 || H) {
                    uint32_t bq[4];
                    ldsm_x4(bq, ubase + offc + (T0 + j - 8) * 256);
                    mma_bf16(acc[j], h64.x, h64.y, l64.x, l64.y, bq[0], bq[1]);
                    mma_bf16(acc[j], h63.x, h63.y, l63.x, l63.y, bq[2], bq[3]);
                }
        }
        TSTAMP(8);
        const bool hi_half = (type == 2 || type == 4);
        if (type != 0) {
            const int pair = H ? c : 5;
            float4* give = reinterpret_cast<float4*>(sm + CV_SM_P + pair * 4096 + (hi_half ? 2048 : 0)) + lane;
            const float4* take = reinterpret_cast<const float4*>(sm + CV_SM_P + pair * 4096 + (hi_half ? 0 : 2048)) + lane;
            const uint32_t pb = smem_u32(sm + CV_SM_CNT) + pair * 16;
#pragma unroll
            for (int j = 0; j < 4; j++)
                give[32 * j] = hi_half ? make_float4(acc[j][0], acc[j][1], acc[j][2], acc[j][3]) : make_float4(acc[j + 4][0], acc[j + 4][1], acc[j + 4][2], acc[j + 4][3]);
            __syncwarp();
            if (lane == 0) mbar_arrive(pb + (hi_half ? 8 : 0));
            mbar_wait(pb + (hi_half ? 0 : 8), 0);
#pragma unroll
            for (int j = 0; j < 4; j++) {
                const float4 v = take[32 * j];
                acc[j][0] = (hi_half ? acc[j + 4][0] : acc[j][0]) + v.x; acc[j][1] = (hi_half ? acc[j + 4][1] : acc[j][1]) + v.y;
                acc[j][2] = (hi_half ? acc[j + 4][2] : acc[j][2]) + v.z; acc[j][3] = (hi_half ? acc[j + 4][3] : acc[j][3]) + v.w;
            }
        }
        const uint32_t dk = __shfl_sync(~0u, dskl, c);
#pragma unroll 1
        for (int rnd = 0; rnd < (type == 0 ? 2 : 1); rnd++) {
            const int Q = 2 * H + (hi_half ? 1 : rnd);
            if (rnd) {
#pragma unroll
                for (int j = 0; j < 4; j++)
#pragma unroll
                    for (int k = 0; k < 4; k++) acc[j][k] = acc[j + 4][k];
            }
            const uint32_t ya = smem_u32(Ys + c * XLEN) + (128 * (4 * Q + (lane >> 4)) + 16 * (lane & 7) + 8 * ((lane >> 3) & 1)) * 2;
#pragma unroll
            for (int j = 0; j < 4; j += 2)
                asm volatile("stmatrix.sync.aligned.m8n8.x4.trans.shared.b16 [%0], {%1,%2,%3,%4};" ::"r"(ya + j * 256),
                             "r"(pack2(acc[j][0], acc[j][1])), "r"(pack2(acc[j][2], acc[j][3])),
                             "r"(pack2(acc[j + 1][0], acc[j + 1][1])), "r"(pack2(acc[j + 1][2], acc[j + 1][3])) : "memory");
            __syncwarp();
            uint4 yv[2], xv[2], uv[2];
#pragma unroll
            for (int k = 0; k < 2; k++) {
                const int t = 512 * Q + 256 * k + 8 * lane, cu = (t + UPADF) >> 3;
                yv[k] = *reinterpret_cast<const uint4*>(Ys + c * XLEN + t);
                xv[k] = *reinterpret_cast<const uint4*>(Xs + c * XLEN + t);
                uv[k] = *reinterpret_cast<const uint4*>(Us + c * ULEN + (cu ^ ((cu >> 3) & 1)) * 8);
            }
#pragma unroll
            for (int k = 0; k < 2; k++)
                *reinterpret_cast<uint4*>(g_xcT + (size_t)(d0 + c) * XCP + 512 * Q + 256 * k + 8 * lane) =
                    make_uint4(fin2(xv[k].x, yv[k].x, uv[k].x, dk), fin2(xv[k].y, yv[k].y, uv[k].y, dk), fin2(xv[k].z, yv[k].z, uv[k].z, dk), fin2(xv[k].w, yv[k].w, uv[k].w, dk));
        }
        if (layer == 1) {
            __syncwarp();
            if (lane == 0) {
                __threadfence();
                asm volatile("red.relaxed.gpu.global.add.u32 [%0], 1;" ::"l"(g_cflag + blockIdx.x) : "memory");
            }
        }
        TSTAMP(4);
    }
    if (layer == 1) {
        const int mb = blockIdx.x >> 3, cg = blockIdx.x & 7;
        if (tid < 16) {
            for (int it = 0; it < SPIN_MAX; it++) {
                uint32_t v;
                asm volatile("ld.acquire.gpu.global.u32 %0, [%1];" : "=r"(v) : "l"(g_cflag + 16 * cg + tid) : "memory");
                if (v == 16 * tag) break;
                __nanosleep(30);
            }
        }
        __syncthreads();
        uint32_t* tl = reinterpret_cast<uint32_t*>(sm);
        uint4 v[3];
#pragma unroll
        for (int k = 0; k < 3; k++) {
            const int i = min(tid + CV_THREADS * k, 1279);
            v[k] = __ldcg(reinterpret_cast<const uint4*>(g_xcT + (size_t)(cg * 80 + (i >> 4)) * XCP + mb * 128) + (i & 15));
        }
#pragma unroll
        for (int k = 0; k < 3; k++) {
            const int i = min(tid + CV_THREADS * k, 1279), c = i >> 4;
            *reinterpret_cast<uint4*>(tl + c * 64 + (((i & 15) ^ (c >> 3)) << 2)) = v[k];
        }
        __syncthreads();
#pragma unroll
        for (int k = 0; k < 2; k++) {
            const int i = tid + CV_THREADS * k, rp = i / 10, q = i - 10 * rp;
            if (i < 640) {
                const uint32_t* sp = tl + 8 * q * 64 + (rp ^ (q << 2));
                uint32_t w[8];
#pragma unroll
                for (int e = 0; e < 8; e++) w[e] = sp[e * 64];
                bf16* dst = xout + (size_t)(mb * 128 + 2 * rp) * DM + cg * 80 + 8 * q;
                asm volatile("st.global.v4.u32 [%0], {%1,%2,%3,%4};" ::"l"(dst), "r"(__byte_perm(w[0], w[1], 0x5410)), "r"(__byte_perm(w[2], w[3], 0x5410)),
                             "r"(__byte_perm(w[4], w[5], 0x5410)), "r"(__byte_perm(w[6], w[7], 0x5410)) : "memory");
                asm volatile("st.global.v4.u32 [%0], {%1,%2,%3,%4};" ::"l"(dst + DM), "r"(__byte_perm(w[0], w[1], 0x7632)), "r"(__byte_perm(w[2], w[3], 0x7632)),
                             "r"(__byte_perm(w[4], w[5], 0x7632)), "r"(__byte_perm(w[6], w[7], 0x7632)) : "memory");
            }
        }
        if (tid == 0 && atomicAdd(&g_done, 1u) == gridDim.x - 1) { g_done = 0; g_epoch = tag; }
    }
    TSTAMP(3);
    TSTAMP(5);
    GSTAMP(g_tim, 14);
    SPAN(3 + 4 * layer, 3);
}

__device__ __forceinline__ void mbar_expect_tx(uint32_t bar, uint32_t bytes) {
    asm volatile("mbarrier.arrive.expect_tx.shared::cta.b64 _, [%0], %1;" ::"r"(bar), "r"(bytes) : "memory");
}
__device__ __forceinline__ void tma_load_2d(uint32_t dst, const void* tmap, int c0, int c1, uint32_t bar) {
    asm volatile("cp.async.bulk.tensor.2d.shared::cluster.global.mbarrier::complete_tx::bytes [%0], [%1, {%3, %4}], [%2];"
                 ::"r"(dst), "l"(tmap), "r"(bar), "r"(c0), "r"(c1) : "memory");
}
__device__ __forceinline__ void fence_async_smem() { asm volatile("fence.proxy.async.shared::cta;" ::: "memory"); }
__device__ __forceinline__ void wgmma_fence() { asm volatile("wgmma.fence.sync.aligned;" ::: "memory"); }
__device__ __forceinline__ void wgmma_commit() { asm volatile("wgmma.commit_group.sync.aligned;" ::: "memory"); }
template <int N> __device__ __forceinline__ void wgmma_wait() { asm volatile("wgmma.wait_group.sync.aligned %0;" ::"n"(N) : "memory"); }
__device__ __forceinline__ uint64_t make_desc(uint32_t addr, uint32_t lbo, uint32_t sbo, uint32_t mode) {
    return (uint64_t)((addr & 0x3FFFF) >> 4) | ((uint64_t)(lbo >> 4) << 16) | ((uint64_t)(sbo >> 4) << 32) | ((uint64_t)mode << 62);
}
template <int TA, int TB>
__device__ __forceinline__ void wgmma_n240(float (&d)[120], uint64_t da, uint64_t db) {
    asm volatile("wgmma.mma_async.sync.aligned.m64n240k16.f32.bf16.bf16 {%0,%1,%2,%3,%4,%5,%6,%7,%8,%9,%10,%11,%12,%13,%14,%15,%16,%17,%18,%19,%20,%21,%22,%23,%24,%25,%26,%27,%28,%29,%30,%31,%32,%33,%34,%35,%36,%37,%38,%39,%40,%41,%42,%43,%44,%45,%46,%47,%48,%49,%50,%51,%52,%53,%54,%55,%56,%57,%58,%59,%60,%61,%62,%63,%64,%65,%66,%67,%68,%69,%70,%71,%72,%73,%74,%75,%76,%77,%78,%79,%80,%81,%82,%83,%84,%85,%86,%87,%88,%89,%90,%91,%92,%93,%94,%95,%96,%97,%98,%99,%100,%101,%102,%103,%104,%105,%106,%107,%108,%109,%110,%111,%112,%113,%114,%115,%116,%117,%118,%119}, %120, %121, 1, 1, 1, %122, %123;"
                 : "+f"(d[0]), "+f"(d[1]), "+f"(d[2]), "+f"(d[3]), "+f"(d[4]), "+f"(d[5]), "+f"(d[6]), "+f"(d[7]), "+f"(d[8]), "+f"(d[9]), "+f"(d[10]), "+f"(d[11]), "+f"(d[12]), "+f"(d[13]), "+f"(d[14]), "+f"(d[15]), "+f"(d[16]), "+f"(d[17]), "+f"(d[18]), "+f"(d[19]), "+f"(d[20]), "+f"(d[21]), "+f"(d[22]), "+f"(d[23]), "+f"(d[24]), "+f"(d[25]), "+f"(d[26]), "+f"(d[27]), "+f"(d[28]), "+f"(d[29]), "+f"(d[30]), "+f"(d[31]), "+f"(d[32]), "+f"(d[33]), "+f"(d[34]), "+f"(d[35]), "+f"(d[36]), "+f"(d[37]), "+f"(d[38]), "+f"(d[39]), "+f"(d[40]), "+f"(d[41]), "+f"(d[42]), "+f"(d[43]), "+f"(d[44]), "+f"(d[45]), "+f"(d[46]), "+f"(d[47]), "+f"(d[48]), "+f"(d[49]), "+f"(d[50]), "+f"(d[51]), "+f"(d[52]), "+f"(d[53]), "+f"(d[54]), "+f"(d[55]), "+f"(d[56]), "+f"(d[57]), "+f"(d[58]), "+f"(d[59]), "+f"(d[60]), "+f"(d[61]), "+f"(d[62]), "+f"(d[63]), "+f"(d[64]), "+f"(d[65]), "+f"(d[66]), "+f"(d[67]), "+f"(d[68]), "+f"(d[69]), "+f"(d[70]), "+f"(d[71]), "+f"(d[72]), "+f"(d[73]), "+f"(d[74]), "+f"(d[75]), "+f"(d[76]), "+f"(d[77]), "+f"(d[78]), "+f"(d[79]), "+f"(d[80]), "+f"(d[81]), "+f"(d[82]), "+f"(d[83]), "+f"(d[84]), "+f"(d[85]), "+f"(d[86]), "+f"(d[87]), "+f"(d[88]), "+f"(d[89]), "+f"(d[90]), "+f"(d[91]), "+f"(d[92]), "+f"(d[93]), "+f"(d[94]), "+f"(d[95]), "+f"(d[96]), "+f"(d[97]), "+f"(d[98]), "+f"(d[99]), "+f"(d[100]), "+f"(d[101]), "+f"(d[102]), "+f"(d[103]), "+f"(d[104]), "+f"(d[105]), "+f"(d[106]), "+f"(d[107]), "+f"(d[108]), "+f"(d[109]), "+f"(d[110]), "+f"(d[111]), "+f"(d[112]), "+f"(d[113]), "+f"(d[114]), "+f"(d[115]), "+f"(d[116]), "+f"(d[117]), "+f"(d[118]), "+f"(d[119])
                 : "l"(da), "l"(db), "n"(TA), "n"(TB));
}

template <int TA, int TB>
__device__ __forceinline__ void wgmma_n80(float (&d)[40], uint64_t da, uint64_t db) {
    asm volatile("wgmma.mma_async.sync.aligned.m64n80k16.f32.bf16.bf16 {%0,%1,%2,%3,%4,%5,%6,%7,%8,%9,%10,%11,%12,%13,%14,%15,%16,%17,%18,%19,%20,%21,%22,%23,%24,%25,%26,%27,%28,%29,%30,%31,%32,%33,%34,%35,%36,%37,%38,%39}, %40, %41, 1, 1, 1, %42, %43;"
                 : "+f"(d[0]), "+f"(d[1]), "+f"(d[2]), "+f"(d[3]), "+f"(d[4]), "+f"(d[5]), "+f"(d[6]), "+f"(d[7]), "+f"(d[8]), "+f"(d[9]), "+f"(d[10]), "+f"(d[11]), "+f"(d[12]), "+f"(d[13]), "+f"(d[14]), "+f"(d[15]), "+f"(d[16]), "+f"(d[17]), "+f"(d[18]), "+f"(d[19]), "+f"(d[20]), "+f"(d[21]), "+f"(d[22]), "+f"(d[23]), "+f"(d[24]), "+f"(d[25]), "+f"(d[26]), "+f"(d[27]), "+f"(d[28]), "+f"(d[29]), "+f"(d[30]), "+f"(d[31]), "+f"(d[32]), "+f"(d[33]), "+f"(d[34]), "+f"(d[35]), "+f"(d[36]), "+f"(d[37]), "+f"(d[38]), "+f"(d[39])
                 : "l"(da), "l"(db), "n"(TA), "n"(TB));
}

__device__ __forceinline__ void bulk_load(uint32_t dst, const void* src, uint32_t bytes, uint32_t bar) {
    asm volatile("cp.async.bulk.shared::cluster.global.mbarrier::complete_tx::bytes [%0], [%1], %2, [%3];"
                 ::"r"(dst), "l"(src), "r"(bytes), "r"(bar) : "memory");
}
__device__ __forceinline__ void tma_store_2d(const void* tmap, int c0, int c1, uint32_t src) {
    asm volatile("cp.async.bulk.tensor.2d.global.shared::cta.bulk_group [%0, {%1, %2}], [%3];" ::"l"(tmap), "r"(c0), "r"(c1), "r"(src) : "memory");
    asm volatile("cp.async.bulk.commit_group;" ::: "memory");
    asm volatile("cp.async.bulk.wait_group.read 0;" ::: "memory");
}
__device__ __forceinline__ void stsm_x4(uint32_t addr, uint32_t r0, uint32_t r1, uint32_t r2, uint32_t r3) {
    asm volatile("stmatrix.sync.aligned.m8n8.x4.shared.b16 [%0], {%1,%2,%3,%4};" ::"r"(addr), "r"(r0), "r"(r1), "r"(r2), "r"(r3) : "memory");
}
__device__ __forceinline__ void stsm_x4_t(uint32_t addr, uint32_t r0, uint32_t r1, uint32_t r2, uint32_t r3) {
    asm volatile("stmatrix.sync.aligned.m8n8.x4.trans.shared.b16 [%0], {%1,%2,%3,%4};" ::"r"(addr), "r"(r0), "r"(r1), "r"(r2), "r"(r3) : "memory");
}
__device__ __forceinline__ void prefetch_tmap(const void* tmap) { asm volatile("prefetch.tensormap [%0];" ::"l"(tmap) : "memory"); }

constexpr int A1_THREADS = 384;
constexpr int A1_NST = 4;
#define A1_PRE0 2
#define A1_SDELAY 1
#define A1_PRE1 1
constexpr int A1_STAGE = 16384 + WQ_STAGE;
constexpr int A1_KVP = 336;
constexpr int A1_SM_KV = 2 * A1_STAGE;
constexpr int A1_SM_O = A1_SM_KV + 144 * A1_KVP;
constexpr int A1_SM_R = A1_NST * A1_STAGE;
constexpr int A1_SM_BAR = A1_SM_R + 20480;
constexpr int A1_SM_CS = A1_SM_BAR + 256;
constexpr int A1_SM_RS = A1_SM_CS + 1024;
constexpr int A1_SM_RED = A1_SM_RS + 1024;
constexpr int A1_SMEM = A1_SM_RED + 1152 + 1024;
static_assert(A1_SM_O % 128 == 0 && A1_SM_O + 20480 <= A1_SM_R, "layout");

template <int L>
__device__ __forceinline__ void a1_mainloop(float (&acc)[120], uint32_t sbase, uint32_t bars, int tile) {
    const int wg = threadIdx.x >> 7;
    constexpr int layer = L; (void)layer;
#pragma unroll 1
    for (int t = 0; t < 10; t++) {
        const int st = t % A1_NST;
        mbar_wait(bars + 8 * st, (t / A1_NST) & 1);
        TSTAMP3(1 + t);
        const uint32_t sa = sbase + st * A1_STAGE;
        wgmma_fence();
#pragma unroll
        for (int kk = 0; kk < 4; kk++)
            wgmma_n240<L, 0>(acc, L ? make_desc(sa + wg * 8192 + kk * 2048, 8192, 1024, 1) : make_desc(sa + wg * 8192 + kk * 32, 16, 1024, 1), make_desc(sa + 16384 + kk * 32, 16, 1024, 1));
        wgmma_commit();
        wgmma_wait<1>();
        if (t > 0 && (threadIdx.x & 127) == 0) mbar_arrive(t < 9 ? bars + 8 * (A1_NST + (t - 1) % A1_NST) : bars + 144);
    }
}

__global__ void __launch_bounds__(A1_THREADS, 1) a1_kernel(const int layer, const bf16* __restrict__ x0, const __grid_constant__ CUtensorMap tmX,
                                                           const __grid_constant__ CUtensorMap tmR, const __grid_constant__ CUtensorMap tmOst) {
    extern __shared__ unsigned char smraw[];
    const uint32_t sbase = (smem_u32(smraw) + 1023) & ~1023u;
    const uint32_t bars = sbase + A1_SM_BAR;
    const uint32_t bar_stat = bars + 64, bar_kv = bars + 72, bar_r = bars + 152;
    const int tid = threadIdx.x, wg = tid >> 7;
    SPAN(1 + 4 * layer, 0);
    const int tile = sm_tile(2 * layer);
    if (tile >= 128) return;
    const int mb = (tile >> 2) & 15, hg = 4 * (tile >> 6) + (tile & 3);
    const uint32_t tag = ld_epoch();
    unsigned char* stg = smraw + (sbase - smem_u32(smraw));
    float* cs = reinterpret_cast<float*>(stg + A1_SM_CS);
    float2* rst = reinterpret_cast<float2*>(stg + A1_SM_RS);
    if (tid == 0) {
        for (int i = 0; i < A1_NST; i++) { mbar_init(bars + 8 * i, 1); mbar_init(bars + 8 * (A1_NST + i), 2); }
        mbar_init(bar_stat, 4);
        for (int i = 0; i < 9; i++) mbar_init(bar_kv + 8 * i, i ? 1 : 4);
        mbar_init(bars + 144, 2);
        mbar_init(bar_r, 1);
        asm volatile("fence.mbarrier_init.release.cluster;" ::: "memory");
    }
    __syncthreads();
    if (wg == 2) {
        const bool is_producer = (tid == 256);
        const int t = tid - 256, pre = layer ? A1_PRE1 : A1_PRE0;
        auto issue_w = [&](int kb) {
            bulk_load(sbase + (kb % A1_NST) * A1_STAGE + 16384, reinterpret_cast<const unsigned char*>(g_wq) + (hg * 10 + kb) * WQ_STAGE, WQ_STAGE, bars + 8 * (kb % A1_NST));
        };
        auto issue_x = [&](int kb) {
            const uint32_t dst = sbase + (kb % A1_NST) * A1_STAGE, full = bars + 8 * (kb % A1_NST);
            if (layer == 0) tma_load_2d(dst, &tmX, kb * 64, mb * 128, full);
            else { tma_load_2d(dst, &tmX, mb * 128, kb * 64, full); tma_load_2d(dst + 8192, &tmX, mb * 128 + 64, kb * 64, full); }
        };
        if (is_producer) {
            prefetch_tmap(&tmX);
            for (int kb = 0; kb < A1_NST; kb++) mbar_expect_tx(bars + 8 * kb, A1_STAGE);
            for (int kb = 0; kb < pre; kb++) { if (layer) issue_w(kb); else issue_x(kb); }
            prefetch_tmap(&tmR);
            prefetch_tmap(&tmOst);
        }
        if (layer || tid < 288) pdl_sync();
        if (is_producer) {
            for (int kb = 0; kb < A1_NST; kb++) {
                if (kb >= pre || layer) issue_x(kb);
                if (kb >= pre || !layer) issue_w(kb);
                if (kb == A1_SDELAY && layer) {
                    mbar_expect_tx(bar_r, 20480);
                    tma_load_2d(sbase + A1_SM_R, &tmR, mb * 128, hg * 80, bar_r); tma_load_2d(sbase + A1_SM_R + 10240, &tmR, mb * 128 + 64, hg * 80, bar_r);
                }
            }
        }
        if (tid >= 288) {
            const int j = tid - 288;
            if (layer == 0) {
                float* red = reinterpret_cast<float*>(stg + A1_SM_RED);
                const int r = j / 6, c6 = j - 6 * r;
                const uint4* src = reinterpret_cast<const uint4*>(x0 + (size_t)(mb * 128 + hg * 16 + r) * DM);
                uint4 v[14];
#pragma unroll
                for (int k = 0; k < 14; k++) v[k] = __ldg(src + min(c6 + 6 * k, 79));
                const float p0 = __uint_as_float(__ldg(reinterpret_cast<const uint32_t*>(src)) << 16);
                float s[2] = {0.f, 0.f}, q[2] = {0.f, 0.f};
#pragma unroll
                for (int k = 0; k < 14; k++) {
                    const uint32_t w[4] = {v[k].x, v[k].y, v[k].z, v[k].w};
                    if (k < 13 || c6 < 2) {
#pragma unroll
                        for (int i = 0; i < 4; i++) {
                            const float a = __uint_as_float(w[i] << 16) - p0, b = __uint_as_float(w[i] & 0xffff0000u) - p0;
                            s[0] += a; s[1] += b; q[0] = fmaf(a, a, q[0]); q[1] = fmaf(b, b, q[1]);
                        }
                    }
                }
                red[j] = s[0] + s[1]; red[96 + j] = q[0] + q[1]; red[192 + j] = p0;
                asm volatile("bar.sync 2, 96;" ::: "memory");
                if (j < 16) {
                    float s0 = 0.f, q0 = 0.f;
#pragma unroll
                    for (int k = 0; k < 6; k++) { s0 += red[6 * j + k]; q0 += red[96 + 6 * j + k]; }
                    const float d = s0 * (1.0f / DM);
                    const uint32_t ms = pack2(red[192 + 6 * j] + d, rbf(sqrtf(rbf(rbf(fmaxf(fmaf(-d, d, q0 * (1.0f / DM)), 0.f)) + 1e-5f))));
                    asm volatile("st.global.cg.u64 [%0], %1;" ::"l"(g_rstat + mb * 128 + hg * 16 + j), "l"(tagw(ms, tag)) : "memory");
                    g_piv[mb * 128 + hg * 16 + j] = __ushort_as_bfloat16((unsigned short)ms);
                }
                pdl_sync();
            } else if (j >= 32) {
                const int ch = j & 7, kg = (j >> 3) & 3;
                const unsigned char* src = stg + A1_SM_R + ((j >> 5) - 1) * 10240;
                mbar_wait(bar_r, 0);
                uint4 v[20];
#pragma unroll
                for (int k = 0; k < 20; k++) v[k] = *reinterpret_cast<const uint4*>(src + (4 * k + kg) * 128 + ((ch ^ ((4 * k + kg) & 7)) << 4));
                const uint4 pv = *reinterpret_cast<const uint4*>(src + (ch << 4));
                float s[8], q[8], p0[8] = {__uint_as_float(pv.x << 16), __uint_as_float(pv.x & 0xffff0000u), __uint_as_float(pv.y << 16), __uint_as_float(pv.y & 0xffff0000u),
                                           __uint_as_float(pv.z << 16), __uint_as_float(pv.z & 0xffff0000u), __uint_as_float(pv.w << 16), __uint_as_float(pv.w & 0xffff0000u)};
#pragma unroll
                for (int i = 0; i < 8; i++) { s[i] = 0.f; q[i] = 0.f; }
#pragma unroll
                for (int k = 0; k < 20; k++) {
                    const uint32_t w[4] = {v[k].x, v[k].y, v[k].z, v[k].w};
#pragma unroll
                    for (int i = 0; i < 4; i++) {
                        const float a = __uint_as_float(w[i] << 16) - p0[2 * i], b = __uint_as_float(w[i] & 0xffff0000u) - p0[2 * i + 1];
                        s[2 * i] += a; s[2 * i + 1] += b; q[2 * i] = fmaf(a, a, q[2 * i]); q[2 * i + 1] = fmaf(b, b, q[2 * i + 1]);
                    }
                }
#pragma unroll
                for (int i = 0; i < 4; i++) {
                    const bool up = kg & 2;
                    const float ss = __shfl_xor_sync(~0u, up ? s[i] : s[i + 4], 16), qq = __shfl_xor_sync(~0u, up ? q[i] : q[i + 4], 16);
                    s[i] = (up ? s[i + 4] : s[i]) + ss; q[i] = (up ? q[i + 4] : q[i]) + qq; p0[i] = up ? p0[i + 4] : p0[i];
                }
#pragma unroll
                for (int i = 0; i < 2; i++) {
                    const bool up = kg & 1;
                    const float ss = __shfl_xor_sync(~0u, up ? s[i] : s[i + 2], 8), qq = __shfl_xor_sync(~0u, up ? q[i] : q[i + 2], 8);
                    s[i] = (up ? s[i + 2] : s[i]) + ss; q[i] = (up ? q[i + 2] : q[i]) + qq; p0[i] = up ? p0[i + 2] : p0[i];
                }
#pragma unroll
                for (int r = 0; r < 2; r++) {
                    const float d = s[r] * (1.0f / 80.0f);
                    st_tag2(g_part + (mb * 8 + hg) * 128 + 64 * r + j - 32, __float_as_uint(p0[r] + d), __float_as_uint(fmaxf(fmaf(-d, s[r], q[r]), 0.f)), tag);
                }
            }
            TSTAMP1T(12, 320);
            if (j < 32) {
#pragma unroll
                for (int h = 0; h < 2; h++) {
                    const int i = j + 32 * h;
                    if (i < 60) {
                        float4 a = make_float4(0.f, 0.f, 0.f, 0.f);
#pragma unroll
                        for (int k = 0; k < 10; k++) {
                            const float4 v = __ldcg(reinterpret_cast<const float4*>(g_csp + k * 1920 + hg * 240) + i);
                            a.x += v.x; a.y += v.y; a.z += v.z; a.w += v.w;
                        }
                        reinterpret_cast<float4*>(cs)[i] = a;
                    }
                }
                TSTAMP1T(13, 288);
            } else if (layer == 0) {
                ulonglong2 v;
                for (int it = 0; it < SPIN_MAX; it++) {
                    v = ld_tag2(reinterpret_cast<const ulonglong2*>(g_rstat + mb * 128) + j - 32);
                    if (tag_ok(v, tag)) break;
                    __nanosleep(100);
                }
                *reinterpret_cast<float4*>(rst + 2 * (j - 32)) = make_float4(__uint_as_float((uint32_t)v.x << 16), __frcp_rn(__uint_as_float((uint32_t)v.x & 0xffff0000u)),
                                                                             __uint_as_float((uint32_t)v.y << 16), __frcp_rn(__uint_as_float((uint32_t)v.y & 0xffff0000u)));
            } else {
                const ulonglong2* gp = g_part + mb * 8 * 128 + j - 32;
                for (int it = 0; it < SPIN_MAX; it++) {
                    if (__all_sync(~0u, tag_ok(ld_tag2(gp + (j & 7) * 128 + 64), tag))) break;
                    __nanosleep(200);
                }
                ulonglong2 pv[16];
                for (int it = 0; it < SPIN_MAX; it++) {
                    bool ok = true;
#pragma unroll
                    for (int k = 0; k < 16; k++) pv[k] = ld_tag2(gp + k * 64);
#pragma unroll
                    for (int k = 0; k < 16; k++) ok = ok && tag_ok(pv[k], tag);
                    if (ok) break;
                    __nanosleep(200);
                }
                float o[4];
#pragma unroll
                for (int r = 0; r < 2; r++) {
                    float mean = 0.f, m2 = 0.f;
#pragma unroll
                    for (int k = 0; k < 8; k++) mean += __uint_as_float((uint32_t)pv[2 * k + r].x);
                    mean *= 0.125f;
#pragma unroll
                    for (int k = 0; k < 8; k++) {
                        const float dm = __uint_as_float((uint32_t)pv[2 * k + r].x) - mean;
                        m2 += fmaf(80.0f * dm, dm, __uint_as_float((uint32_t)pv[2 * k + r].y));
                    }
                    o[2 * r] = rbf(mean);
                    o[2 * r + 1] = __frcp_rn(rbf(sqrtf(rbf(rbf(m2 * (1.0f / DM)) + 1e-5f))));
                }
                const int row = ((j >> 5) - 1) * 64 + (j & 7) * 8 + ((j >> 3) & 3) * 2;
                *reinterpret_cast<float4*>(rst + row) = make_float4(o[0], o[1], o[2], o[3]);
                if (hg == 0) *reinterpret_cast<uint32_t*>(g_piv + SEQ + mb * 128 + row) = __byte_perm(__float_as_uint(o[0]), __float_as_uint(o[2]), 0x7632);
            }
            TSTAMP1T(7, 320);
        } else if (is_producer) {
            for (int kb = A1_NST; kb < 10; kb++) {
                mbar_wait(bars + 8 * (A1_NST + kb % A1_NST), ((kb / A1_NST) - 1) & 1);
                mbar_expect_tx(bars + 8 * (kb % A1_NST), A1_STAGE);
                issue_x(kb); issue_w(kb);
            }
            TSTAMP1T(6, 256);
        }
        __syncwarp();
        if ((tid & 31) == 0) mbar_arrive(bar_stat);
        mbar_wait(bars + 144, 0);
        mbar_wait(bars + 8 * (A1_NST + 3), 1);
        TSTAMP1T(9, 256);
        const ulonglong2* hin = g_halo + ((size_t)(layer * 16 + mb - 1) * 8 + hg) * 640 + t;
        ulonglong2 hv[5];
        if (mb > 0) {
            for (int it = 0; it < SPIN_MAX; it++) {
                bool ok = true;
#pragma unroll
                for (int k = 0; k < 5; k++) hv[k] = ld_tag2(hin + 128 * k);
#pragma unroll
                for (int k = 0; k < 5; k++) ok = ok && tag_ok(hv[k], tag);
                if (ok) break;
            }
        } else {
#pragma unroll
            for (int k = 0; k < 5; k++) hv[k] = make_ulonglong2(0, 0);
        }
        TSTAMP1T(11, 256);
        unsigned char* hd = stg + A1_SM_KV + ((t & 31) >> 2) * A1_KVP + (t & 3) * 4 + (t >> 5) * 16;
#pragma unroll
        for (int k = 0; k < 5; k++) {
            *reinterpret_cast<uint32_t*>(hd + 64 * k) = (uint32_t)hv[k].x;
            *reinterpret_cast<uint32_t*>(hd + 64 * k + 8 * A1_KVP) = (uint32_t)hv[k].y;
        }
        __syncwarp();
        if ((tid & 31) == 0) mbar_arrive(bar_kv);
    } else {
        pdl_sync();
        SPAN(1 + 4 * layer, 1);
        TSTAMP1(0);
        if (threadIdx.x == 0) { GSTAMP(g_tim1, 15); }
        TSTAMP3(0);
        float acc[120];
#pragma unroll
        for (int i = 0; i < 120; i++) acc[i] = 0.f;
        if (layer == 0) a1_mainloop<0>(acc, sbase, bars, tile); else a1_mainloop<1>(acc, sbase, bars, tile);
        const int lane = tid & 31, warp = tid >> 5, g = lane >> 2, t = lane & 3;
        mbar_wait(bar_stat, 0);
        mbar_wait(bars + 8 * (A1_NST + 3), 1);
        const float2 sa_ = rst[16 * warp + g], sb_ = rst[16 * warp + g + 8];
        wgmma_wait<0>();
        TSTAMP1(2);
        uint32_t f[30][2];
        auto norm = [&](int j0) {
            float2 cc[10];
#pragma unroll
            for (int j = 0; j < 10; j++) cc[j] = *reinterpret_cast<const float2*>(cs + 8 * (j0 + j) + 2 * t);
#pragma unroll
            for (int j = 0; j < 10; j++) {
                const float* a = acc + 4 * (j0 + j);
                f[j0 + j][0] = pack2(fmaf(-sa_.x, cc[j].x, a[0]) * sa_.y, fmaf(-sa_.x, cc[j].y, a[1]) * sa_.y);
                f[j0 + j][1] = pack2(fmaf(-sb_.x, cc[j].x, a[2]) * sb_.y, fmaf(-sb_.x, cc[j].y, a[3]) * sb_.y);
            }
        };
        norm(10); norm(20);
        if (warp == 7) {
            ulonglong2* hout = g_halo + ((size_t)(layer * 16 + mb) * 8 + hg) * 640 + lane;
#pragma unroll
            for (int j = 0; j < 20; j++) st_tag2(hout + 32 * j, f[10 + j][0], f[10 + j][1], tag);
        }
        const uint32_t kvw = sbase + A1_SM_KV + 16 * warp * A1_KVP;
        const uint32_t mrow = kvw + (lane & 15) * A1_KVP + (lane >> 4) * 16;
#pragma unroll
        for (int j = 0; j < 20; j += 2) stsm_x4(mrow + 16 * A1_KVP + 16 * j, f[10 + j][0], f[10 + j][1], f[11 + j][0], f[11 + j][1]);
        __syncwarp();
        if (lane == 0) mbar_arrive(bar_kv + 8 * (warp + 1));
        norm(0);
        TSTAMP1T(10, 64);
        float sc[4][4][4];
        uint32_t qs[4][2];
#pragma unroll
        for (int h = 0; h < 4; h++) {
            const int jb = 5 * (h >> 1) + 3 * (h & 1), js = 5 * (h >> 1) + 2;
            qs[h][0] = (t >> 1) == (h & 1) ? f[js][0] : 0u; qs[h][1] = (t >> 1) == (h & 1) ? f[js][1] : 0u;
#pragma unroll
            for (int nt = 2; nt < 4; nt++) {
#pragma unroll
                for (int e = 0; e < 4; e++) sc[h][nt][e] = 0.f;
                mma_bf16(sc[h][nt], f[jb][0], f[jb][1], f[jb + 1][0], f[jb + 1][1], f[10 + jb][nt - 2], f[11 + jb][nt - 2]);
                mma_bf16_k8(sc[h][nt], qs[h][0], qs[h][1], f[10 + js][nt - 2]);
            }
        }
        mbar_wait(bar_kv + 8 * warp, 0);
        TSTAMP1(8);
        uint32_t kp[10][2];
#pragma unroll
        for (int j = 0; j < 10; j += 2) ldsm_x4(&kp[j][0], mrow + 16 * j);
#pragma unroll
        for (int h = 0; h < 4; h++) {
            const int jb = 5 * (h >> 1) + 3 * (h & 1), js = 5 * (h >> 1) + 2;
#pragma unroll
            for (int nt = 0; nt < 2; nt++) {
#pragma unroll
                for (int e = 0; e < 4; e++) sc[h][nt][e] = 0.f;
                mma_bf16(sc[h][nt], f[jb][0], f[jb][1], f[jb + 1][0], f[jb + 1][1], kp[jb][nt], kp[jb + 1][nt]);
                mma_bf16_k8(sc[h][nt], qs[h][0], qs[h][1], kp[js][nt]);
            }
        }
        uint32_t vb[10][4];
#pragma unroll
        for (int j = 0; j < 10; j++) ldsm_x4_t(vb[j], kvw + lane * A1_KVP + 160 + 16 * j);
        TSTAMP1T(3, 64);
        const bool odd = g & 1, hi = t > (g >> 1), edge = (mb | warp) == 0;
        float p[4][4], mx[4][2], sum[4][2];
#pragma unroll
        for (int h = 0; h < 4; h++) {
#pragma unroll
            for (int r = 0; r < 2; r++) {
                const float a = odd ? sc[h][1 + r][2 * r + 1] : sc[h][1 + r][2 * r];
                const float b0 = odd ? sc[h][r][2 * r + 1] : sc[h][r][2 * r], b1 = odd ? sc[h][2 + r][2 * r + 1] : sc[h][2 + r][2 * r];
                const uint32_t w = pack2(a, hi ? b0 : b1);
                const uint32_t w2 = pack2(__uint_as_float(w << 16) * 0.22360679774997896f, __uint_as_float(w & 0xffff0000u) * 0.22360679774997896f);
                p[h][2 * r] = __uint_as_float(w2 << 16); p[h][2 * r + 1] = __uint_as_float(w2 & 0xffff0000u);
            }
            if (edge) {
                p[h][0] = -1.0e9f;
                if (hi) { p[h][1] = -1.0e9f; p[h][3] = -1.0e9f; }
            }
            mx[h][0] = fmaxf(p[h][0], p[h][1]); mx[h][1] = fmaxf(p[h][2], p[h][3]);
        }
#pragma unroll
        for (int o = 1; o <= 2; o <<= 1)
#pragma unroll
            for (int h = 0; h < 4; h++)
#pragma unroll
                for (int r = 0; r < 2; r++) mx[h][r] = fmaxf(mx[h][r], __shfl_xor_sync(~0u, mx[h][r], o));
#pragma unroll
        for (int h = 0; h < 4; h++)
#pragma unroll
            for (int r = 0; r < 2; r++) {
                p[h][2 * r] = __expf(p[h][2 * r] - mx[h][r]); p[h][2 * r + 1] = __expf(p[h][2 * r + 1] - mx[h][r]);
                sum[h][r] = p[h][2 * r] + p[h][2 * r + 1];
            }
#pragma unroll
        for (int o = 1; o <= 2; o <<= 1)
#pragma unroll
            for (int h = 0; h < 4; h++)
#pragma unroll
                for (int r = 0; r < 2; r++) sum[h][r] += __shfl_xor_sync(~0u, sum[h][r], o);
        TSTAMP1T(5, 64);
        const uint32_t selA = odd ? 0x1044u : 0x4410u, selB = odd ? 0x3244u : 0x4432u, selH = hi ? selB : 0x4444u, selL = hi ? 0x4444u : selB;
        const uint32_t orow = sbase + A1_SM_O + (16 * warp + (lane & 15)) * 160 + (lane >> 4) * 16;
        uint32_t ob[10][2];
#pragma unroll
        for (int P = 0; P < 2; P++) {
            float os[2][4];
#pragma unroll
            for (int e = 0; e < 2; e++) {
                const int h = 2 * P + e;
                const float i0 = __fdividef(1.0f, sum[h][0]), i1 = __fdividef(1.0f, sum[h][1]);
                const uint32_t w0 = pack2(p[h][0] * i0, p[h][1] * i0), w1 = pack2(p[h][2] * i1, p[h][3] * i1);
                const uint32_t a00 = __byte_perm(w0, 0, selH), a02 = __byte_perm(w0, 0, selA), a03 = __byte_perm(w1, 0, selH);
                const uint32_t a10 = __byte_perm(w0, 0, selL), a11 = __byte_perm(w1, 0, selA), a13 = __byte_perm(w1, 0, selL);
#pragma unroll
                for (int dt = 0; dt < 3; dt++) {
                    const int j = 5 * P + (dt < 2 ? 3 * e + dt : 2);
                    float o[4] = {0.f, 0.f, 0.f, 0.f};
                    mma_bf16(o, a00, 0u, a02, a03, vb[j][0], vb[j][1]);
                    mma_bf16(o, a10, a11, 0u, a13, vb[j][2], vb[j][3]);
                    if (dt < 2) { ob[j][0] = pack2(o[0], o[1]); ob[j][1] = pack2(o[2], o[3]); }
                    else { os[e][0] = o[0]; os[e][1] = o[1]; os[e][2] = o[2]; os[e][3] = o[3]; }
                }
            }
            ob[5 * P + 2][0] = t < 2 ? pack2(os[0][0], os[0][1]) : pack2(os[1][0], os[1][1]);
            ob[5 * P + 2][1] = t < 2 ? pack2(os[0][2], os[0][3]) : pack2(os[1][2], os[1][3]);
        }
#pragma unroll
        for (int j = 0; j < 10; j += 2) stsm_x4(orow + 16 * j, ob[j][0], ob[j][1], ob[j + 1][0], ob[j + 1][1]);
        fence_async_smem();
        __syncwarp();
        if (lane == 0) tma_store_2d(&tmOst, hg * 80, mb * 128 + 16 * warp, sbase + A1_SM_O + 16 * warp * 160);
        TSTAMP1T(4, 64);
        TSTAMP1(1);
        GSTAMP(g_tim1, 14);
        SPAN(1 + 4 * layer, 3);
    }
}

constexpr int A2_THREADS = 288;
constexpr int A2_NA = 6;
constexpr int A2_WPRE = 4;
constexpr int A2_SM_A = 10 * WO_STAGE;
constexpr int A2_SM_R = A2_SM_A + A2_NA * 16384;
constexpr int A2_SM_BAR = A2_SM_R + 20480;
constexpr int A2_SMEM = A2_SM_BAR + 256 + 1024;

__global__ void __launch_bounds__(A2_THREADS, 1) a2_kernel(const int layer, const __grid_constant__ CUtensorMap tmO, const __grid_constant__ CUtensorMap tmR,
                                                           const __grid_constant__ CUtensorMap tmX1) {
    extern __shared__ unsigned char smraw[];
    const uint32_t sbase = (smem_u32(smraw) + 1023) & ~1023u;
    const uint32_t bars = sbase + A2_SM_BAR, bar_e = bars + 80, bar_r = bars + 128, bar_w = bars + 136;
    const int tid = threadIdx.x, wg = tid >> 7;
    SPAN(2 + 4 * layer, 0);
    const int tile = sm_tile(2 * layer + 1);
    if (tile >= 128) return;
    const int mb = tile >> 3, cg = tile & 7;
    if (tid == 256) {
        for (int i = 0; i < 10; i++) mbar_init(bars + 8 * i, 1);
        for (int i = 0; i < A2_NA; i++) mbar_init(bar_e + 8 * i, 2);
        mbar_init(bar_r, 1); mbar_init(bar_w, 1); mbar_init(bar_w + 8, 1);
        asm volatile("fence.mbarrier_init.release.cluster;" ::: "memory");
        mbar_expect_tx(bar_w, A2_WPRE * WO_STAGE);
        bulk_load(sbase, reinterpret_cast<const unsigned char*>(g_wo) + cg * 10 * WO_STAGE, A2_WPRE * WO_STAGE, bar_w);
        prefetch_tmap(&tmO);
        for (int kb = 0; kb < 10; kb++) mbar_expect_tx(bars + 8 * kb, 16384);
        mbar_expect_tx(bar_w + 8, (10 - A2_WPRE) * WO_STAGE);
        mbar_expect_tx(bar_r, 20480);
        prefetch_tmap(&tmR);
        prefetch_tmap(&tmX1);
    }
    __syncthreads();
    pdl_sync();
    SPAN(2 + 4 * layer, 1);
    TSTAMP2(0);
    TSTAMP4(0);
    if (threadIdx.x == 0) { GSTAMP(g_tim2, 15); }
    if (wg == 2) {
        if (tid == 256) {
            for (int kb = 0; kb < 10; kb++) {
                if (kb >= A2_NA) mbar_wait(bar_e + 8 * (kb - A2_NA), 0);
                tma_load_2d(sbase + A2_SM_A + (kb % A2_NA) * 16384, &tmO, kb * 64, mb * 128, bars + 8 * kb);
                if (kb == 2) bulk_load(sbase + A2_WPRE * WO_STAGE, reinterpret_cast<const unsigned char*>(g_wo) + (cg * 10 + A2_WPRE) * WO_STAGE, (10 - A2_WPRE) * WO_STAGE, bar_w + 8);
                if (kb == A2_NA - 1) {
                    if (layer == 0) tma_load_2d(sbase + A2_SM_R, &tmR, cg * 80, mb * 128, bar_r);
                    else { tma_load_2d(sbase + A2_SM_R, &tmR, mb * 128, cg * 80, bar_r); tma_load_2d(sbase + A2_SM_R + 10240, &tmR, mb * 128 + 64, cg * 80, bar_r); }
                }
            }
        }
    } else {
        const int lane = tid & 31, warp = tid >> 5, g = lane >> 2, t = lane & 3;
        const int row = layer * SEQ + mb * 128 + 16 * warp + g;
        const unsigned short pv0 = __ldcg(reinterpret_cast<const unsigned short*>(g_piv) + row), pv1 = __ldcg(reinterpret_cast<const unsigned short*>(g_piv) + row + 8);
        float acc[40];
#pragma unroll
        for (int i = 0; i < 40; i++) acc[i] = 0.f;
        for (int kb = 0; kb < 10; kb++) {
            if (kb == 0) TSTAMP4(11);
            if (kb == 0 || kb == A2_WPRE) mbar_wait(kb ? bar_w + 8 : bar_w, 0);
            mbar_wait(bars + 8 * kb, 0);
            TSTAMP4(1 + kb);
            const uint32_t sa = sbase + A2_SM_A + (kb % A2_NA) * 16384 + wg * 8192, sb = sbase + kb * WO_STAGE;
            wgmma_fence();
#pragma unroll
            for (int kk = 0; kk < 4; kk++) wgmma_n80<0, 0>(acc, make_desc(sa + kk * 32, 16, 1024, 1), make_desc(sb + kk * 32, 16, 1024, 1));
            wgmma_commit();
            wgmma_wait<1>();
            if (kb > 0 && kb <= A2_NA && (tid & 127) == 0) mbar_arrive(bar_e + 8 * (kb - 1));
        }
        const uint32_t trow = ((lane & 7) + 8 * (lane >> 4)) * 128 + (((2 * (warp & 3) + ((lane >> 3) & 1)) ^ (lane & 7)) << 4);
        uint32_t xr[10][2];
        mbar_wait(bar_r, 0);
        if (layer == 0) {
#pragma unroll
            for (int j = 0; j < 10; j += 2) ldsm_x4(&xr[j][0], sbase + A2_SM_R + (16 * warp + (lane & 15)) * 160 + (lane >> 4) * 16 + 16 * j);
        } else {
#pragma unroll
            for (int j = 0; j < 10; j += 2) ldsm_x4_t(&xr[j][0], sbase + A2_SM_R + wg * 10240 + trow + 1024 * j);
        }
        mbar_wait(bar_e + 8 * (4 + wg), 0);
        wgmma_wait<0>();
        TSTAMP2(1);
        const float p0 = __uint_as_float((uint32_t)pv0 << 16), p1 = __uint_as_float((uint32_t)pv1 << 16);
        float s[4] = {0.f, 0.f, 0.f, 0.f};
#pragma unroll
        for (int j = 0; j < 10; j++) {
#pragma unroll
            for (int hh = 0; hh < 2; hh++) {
                const uint32_t a = pack2(acc[4 * j + 2 * hh], acc[4 * j + 2 * hh + 1]);
                const __nv_bfloat162 r = __hadd2_rn(*reinterpret_cast<const __nv_bfloat162*>(&xr[j][hh]), *reinterpret_cast<const __nv_bfloat162*>(&a));
                const uint32_t w = *reinterpret_cast<const uint32_t*>(&r);
                xr[j][hh] = w;
                const float d0 = __uint_as_float(w << 16) - (hh ? p1 : p0), d1 = __uint_as_float(w & 0xffff0000u) - (hh ? p1 : p0);
                s[2 * hh] += d0 + d1;
                s[2 * hh + 1] = fmaf(d0, d0, fmaf(d1, d1, s[2 * hh + 1]));
            }
        }
        const uint32_t so = sbase + A2_SM_A + (4 + wg) * 16384;
#pragma unroll
        for (int j = 0; j < 10; j += 2) stsm_x4_t(so + trow + 1024 * j, xr[j][0], xr[j][1], xr[j + 1][0], xr[j + 1][1]);
        fence_async_smem();
        TSTAMP2(2);
#pragma unroll
        for (int o = 1; o <= 2; o <<= 1)
#pragma unroll
            for (int i = 0; i < 4; i++) s[i] += __shfl_xor_sync(~0u, s[i], o);
        if (t < 2) asm volatile("red.relaxed.gpu.global.add.v2.f32 [%0], {%1, %2};" ::"l"(g_sum + layer * SEQ + (g >> 1) * 512 + (mb * 16 + 2 * warp + t) * 2 + (g & 1)), "f"(t ? s[2] : s[0]), "f"(t ? s[3] : s[1]) : "memory");
        if (wg) asm volatile("bar.sync 2, 128;" ::: "memory"); else asm volatile("bar.sync 1, 128;" ::: "memory");
        TSTAMP2(3);
        if ((tid & 127) == 0) tma_store_2d(&tmX1, mb * 128 + 64 * wg, cg * 80, so);
        TSTAMP2(4);
        GSTAMP(g_tim2, 14);
        SPAN(2 + 4 * layer, 3);
    }
}

static int h_nsm;
static CUtensorMap h_tmX0, h_tmX1, h_tmOst, h_tmO, h_tmR0, h_tmR1, h_tmX1st;
typedef CUresult (*PFN_encodeTiled)(CUtensorMap*, CUtensorMapDataType, cuuint32_t, void*, const cuuint64_t*, const cuuint64_t*,
                                    const cuuint32_t*, const cuuint32_t*, CUtensorMapInterleave, CUtensorMapSwizzle,
                                    CUtensorMapL2promotion, CUtensorMapFloatOOBfill);
static void make_tmap(CUtensorMap* tm, const void* ptr, uint64_t cols, uint64_t rows, uint32_t bc, uint32_t br, CUtensorMapSwizzle sw, uint64_t pitch = 0) {
    static PFN_encodeTiled fn = nullptr;
    if (!fn) {
        void* p = nullptr; cudaDriverEntryPointQueryResult qr;
        cudaGetDriverEntryPoint("cuTensorMapEncodeTiled", &p, cudaEnableDefault, &qr);
        fn = (PFN_encodeTiled)p;
    }
    cuuint64_t dims[2] = {cols, rows}; cuuint64_t strides[1] = {(pitch ? pitch : cols) * 2};
    cuuint32_t box[2] = {bc, br}; cuuint32_t es[2] = {1, 1};
    fn(tm, CU_TENSOR_MAP_DATA_TYPE_BFLOAT16, 2, const_cast<void*>(ptr), dims, strides, box, es, CU_TENSOR_MAP_INTERLEAVE_NONE, sw,
       CU_TENSOR_MAP_L2_PROMOTION_L2_128B, CU_TENSOR_MAP_FLOAT_OOB_FILL_NONE);
}
template <typename... Args>
static void launch_pdl(void (*kern)(Args...), int grid, int block, int smem, Args... args) {
    cudaLaunchConfig_t cfg = {};
    cfg.gridDim = dim3(grid); cfg.blockDim = dim3(block); cfg.dynamicSmemBytes = smem; cfg.stream = cudaStreamPerThread;
    cudaLaunchAttribute at[1];
    at[0].id = cudaLaunchAttributeProgrammaticStreamSerialization; at[0].val.programmaticStreamSerializationAllowed = 1;
    cfg.attrs = at; cfg.numAttrs = 1;
    cudaLaunchKernelEx(&cfg, kern, args...);
}
static void launch_stage(int k, void* const* d_in, void* d_out) {
    const KgIn kg = {(const bf16*)d_in[4], (const bf16*)d_in[5], (const bf16*)d_in[6], (const bf16*)d_in[7], (const bf16*)d_in[8], (const bf16*)d_in[0], (const bf16*)d_in[1], (const bf16*)d_in[2]};
    switch (k) {
        case 0: kgen_kernel<<<DM, KG_THREADS, 0, cudaStreamPerThread>>>(kg); break;
        case 1: launch_pdl(a1_kernel, h_nsm, A1_THREADS, A1_SMEM, 0, (const bf16*)d_in[0], h_tmX0, h_tmR1, h_tmOst); break;
        case 2: launch_pdl(a2_kernel, h_nsm, A2_THREADS, A2_SMEM, 0, h_tmO, h_tmR0, h_tmX1st); break;
        case 3: launch_pdl(conv_kernel, DM / CV_CPB, CV_THREADS, CV_SMEM, (const bf16*)d_in[9], 0, (bf16*)d_out); break;
        case 5: launch_pdl(a1_kernel, h_nsm, A1_THREADS, A1_SMEM, 1, (const bf16*)d_in[0], h_tmX1, h_tmR1, h_tmOst); break;
        case 6: launch_pdl(a2_kernel, h_nsm, A2_THREADS, A2_SMEM, 1, h_tmO, h_tmR1, h_tmX1st); break;
        case 7: launch_pdl(conv_kernel, DM / CV_CPB, CV_THREADS, CV_SMEM, (const bf16*)d_in[9], 1, (bf16*)d_out); break;
        default: break;
    }
}
static int n_stage_kernels() { return 9; }
static const char* stage_name(int k) { const char* n[] = {"kgen", "a1", "a2", "conv", "tr", "a1", "a2", "conv", "tr"}; return n[k]; }

extern "C" void kernel_launch(void* const* d_in, const int* in_sizes, int n_in, void* d_out, int out_size) {
    (void)in_sizes; (void)n_in; (void)out_size;
    static bool init = false;
    if (!init) {
        cudaFuncSetAttribute(conv_kernel, cudaFuncAttributeMaxDynamicSharedMemorySize, CV_SMEM);
        cudaFuncSetAttribute(kgen_kernel, cudaFuncAttributePreferredSharedMemoryCarveout, 100);
        cudaFuncSetAttribute(a1_kernel, cudaFuncAttributeMaxDynamicSharedMemorySize, A1_SMEM);
        cudaFuncSetAttribute(a2_kernel, cudaFuncAttributeMaxDynamicSharedMemorySize, A2_SMEM);
        int dev; cudaGetDevice(&dev); cudaDeviceGetAttribute(&h_nsm, cudaDevAttrMultiProcessorCount, dev);
        if (h_nsm != 132) h_nsm = 128;
        void *po, *px1, *px2;
        cudaGetSymbolAddress(&po, g_o); cudaGetSymbolAddress(&px1, g_x1T); cudaGetSymbolAddress(&px2, g_xcT);
        make_tmap(&h_tmO, po, 640, 2048, 64, 128, CU_TENSOR_MAP_SWIZZLE_128B);
        make_tmap(&h_tmOst, po, 640, 2048, 80, 16, CU_TENSOR_MAP_SWIZZLE_NONE);
        make_tmap(&h_tmX0, d_in[0], 640, 2048, 64, 128, CU_TENSOR_MAP_SWIZZLE_128B);
        make_tmap(&h_tmX1, px2, 2048, 640, 64, 64, CU_TENSOR_MAP_SWIZZLE_128B, XCP);
        make_tmap(&h_tmR0, d_in[0], 640, 2048, 80, 128, CU_TENSOR_MAP_SWIZZLE_NONE);
        make_tmap(&h_tmR1, px2, 2048, 640, 64, 80, CU_TENSOR_MAP_SWIZZLE_128B, XCP);
        make_tmap(&h_tmX1st, px1, 2048, 640, 64, 80, CU_TENSOR_MAP_SWIZZLE_128B, XCP);
        init = true;
    }
    for (int k = 0; k < n_stage_kernels(); k++) launch_stage(k, d_in, d_out);
}
```

```cpp
#include <cuda_runtime.h>
#include <cuda_bf16.h>
#include <stdint.h>
#include <cuda.h>

typedef __nv_bfloat16 bf16;

constexpr int SEQ = 2048;
constexpr int DM = 640;
constexpr int NMODE = 192;

__device__ __forceinline__ float bf2f(bf16 v) { return __bfloat162float(v); }
__device__ __forceinline__ float rbf(float v) {
    uint32_t r;
    asm("cvt.rn.bf16x2.f32 %0, %1, %2;" : "=r"(r) : "f"(v), "f"(0.f));
    return __uint_as_float(r);
}
__device__ __forceinline__ uint32_t pack2(float lo, float hi) {
    __nv_bfloat162 t = __floats2bfloat162_rn(lo, hi);
    return *reinterpret_cast<uint32_t*>(&t);
}
__device__ __forceinline__ void pdl_sync() {
    asm volatile("griddepcontrol.wait;" ::: "memory");
    asm volatile("griddepcontrol.launch_dependents;" ::: "memory");
}
__device__ __forceinline__ float sqrt_apx(float v) { float r; asm("sqrt.approx.ftz.f32 %0, %1;" : "=f"(r) : "f"(v)); return r; }
__device__ __forceinline__ float rcp_apx(float v) { float r; asm("rcp.approx.ftz.f32 %0, %1;" : "=f"(r) : "f"(v)); return r; }
__device__ __forceinline__ uint32_t smem_u32(const void* p) { return (uint32_t)__cvta_generic_to_shared(p); }

constexpr int TPAD = 16;
constexpr int DLEN = 544;
constexpr int TAP_W2 = DLEN * 8, TAP_W3 = TAP_W2 + 768, TAP_C = TAP_W3 + 768, TAPB = TAP_C + 384;
__device__ __align__(128) uint4 g_tap[DM * 128];
#define XPAD 64
constexpr int XCP = SEQ + XPAD;
__device__ __align__(128) bf16 g_x1T[DM * XCP];
__device__ __align__(128) bf16 g_xcT[DM * XCP];
__device__ __align__(128) bf16 g_o[SEQ * DM];
constexpr int WQ_STAGE = 240 * 128, WO_STAGE = 80 * 128;
__device__ __align__(128) uint4 g_wq[8 * 10 * WQ_STAGE / 16];
__device__ __align__(128) uint4 g_wo[8 * 10 * WO_STAGE / 16];
__device__ __align__(16) float g_csp[10 * 1920];
__device__ __align__(16) float2 g_sum[2 * SEQ];
__device__ __align__(16) bf16 g_piv[2 * SEQ];
__device__ __align__(128) bf16 g_yT[DM * XCP];
__device__ uint32_t g_epoch;
__device__ __align__(16) unsigned long long g_rstat[SEQ];
__device__ ulonglong2 g_part[16 * 8 * 128];
__device__ ulonglong2 g_halo[2 * 16 * 8 * 640];
__device__ __forceinline__ unsigned long long tagw(uint32_t payload, uint32_t tag) { return ((unsigned long long)tag << 32) | payload; }
__device__ __forceinline__ void st_tag2(ulonglong2* p, uint32_t a, uint32_t b, uint32_t tag) {
    asm volatile("st.global.cg.v2.u64 [%0], {%1, %2};" ::"l"(p), "l"(tagw(a, tag)), "l"(tagw(b, tag)) : "memory");
}
__device__ __forceinline__ ulonglong2 ld_tag2(const ulonglong2* p) {
    ulonglong2 v;
    asm volatile("ld.relaxed.gpu.global.v2.u64 {%0, %1}, [%2];" : "=l"(v.x), "=l"(v.y) : "l"(p) : "memory");
    return v;
}
__device__ __forceinline__ bool tag_ok(ulonglong2 v, uint32_t tag) { return (uint32_t)(v.x >> 32) == tag && (uint32_t)(v.y >> 32) == tag; }
__device__ __forceinline__ uint32_t ld_epoch() { uint32_t v; asm volatile("ld.relaxed.gpu.global.u32 %0, [%1];" : "=r"(v) : "l"(&g_epoch) : "memory"); return v + 1; }
constexpr int SPIN_MAX = 1 << 20;
__device__ uint32_t g_started[4];
__device__ __forceinline__ int sm_tile(int slot) {
    if (gridDim.x == 128) return blockIdx.x;
    uint32_t s;
    asm volatile("mov.u32 %0, %smid;" : "=r"(s));
    const int h = ((int)s - 64) >> 1;
    const int tile = s < 64 ? ((s >> 1) & 7) * 16 + (s >> 4) * 2 + (s & 1) : s < 120 ? (1 + h % 7) * 16 + 8 + (h / 7) * 2 + (s & 1) : s < 124 || s > 131 ? 128 : s - 116;
    if (threadIdx.x == 0) {
        asm volatile("red.relaxed.gpu.global.add.u32 [%0], 1;" ::"l"(g_started + slot) : "memory");
        if (tile >= 128) {
            const uint32_t want = ld_epoch() * gridDim.x;
            pdl_sync();
#pragma unroll 1
            for (int it = 0; it < SPIN_MAX; it++) {
                uint32_t v;
                asm volatile("ld.relaxed.gpu.global.u32 %0, [%1];" : "=r"(v) : "l"(g_started + slot) : "memory");
                if ((int)(v - want) >= 0) break;
                __nanosleep(100);
            }
        }
    }
    return tile;
}
#define DBG_SYMS
#define TSTAMP(i)
#define TSTAMP1(i)
#define TSTAMP1T(i, t)
#define TSTAMP1X(i, t)
#define SPAN(k, i)
#define GSTAMP(arr, i)
#define TSTAMP2(i)
#define TSTAMP3(i)
#define TSTAMP4(i)
#define TSTAMPK(i, t)

__device__ __forceinline__ float2 cexp_at(float wr2, float wi, float p) {
    float er;
    asm("ex2.approx.ftz.f32 %0, %1;" : "=f"(er) : "f"(wr2 * p));
    float th = wi * p;
    const float k = rintf(th * 0.15915494309189535f);
    th = fmaf(k, -6.2831854820251465f, th);
    th = fmaf(k, 1.7484555314695172e-7f, th);
    return make_float2(er * __cosf(th), er * __sinf(th));
}
__device__ __forceinline__ float2 cmul(float2 a, float2 b) {
    return make_float2(fmaf(a.x, b.x, -a.y * b.y), fmaf(a.x, b.y, a.y * b.x));
}
__device__ __forceinline__ float2 csqr(float2 a) { return make_float2(fmaf(a.x, a.x, -a.y * a.y), (a.x + a.x) * a.y); }
__device__ __forceinline__ uint32_t packh(float2 v) {
    uint32_t r;
    asm("cvt.rn.f16x2.f32 %0, %1, %2;" : "=r"(r) : "f"(v.y), "f"(v.x));
    return r;
}
__device__ __forceinline__ void mma_f16(float* d, uint32_t a0, uint32_t a1, uint32_t a2, uint32_t a3, uint32_t b0, uint32_t b1) {
    asm volatile("mma.sync.aligned.m16n8k16.row.col.f32.f16.f16.f32 {%0,%1,%2,%3}, {%4,%5,%6,%7}, {%8,%9}, {%0,%1,%2,%3};"
                 : "+f"(d[0]), "+f"(d[1]), "+f"(d[2]), "+f"(d[3]) : "r"(a0), "r"(a1), "r"(a2), "r"(a3), "r"(b0), "r"(b1));
}

struct KgIn { const bf16 *logA, *Aim, *Cre, *Cim, *logdt, *x, *wqkv, *wo; };
constexpr int KG_THREADS = NMODE / 2;

__global__ void __launch_bounds__(KG_THREADS, 5) kgen_kernel(const KgIn in) {
    __shared__ __align__(128) uint4 tab[3 * 896];
    __shared__ __align__(16) unsigned short E[1024];
    const int d = blockIdx.x, tid = threadIdx.x, lane = tid & 31, warp = tid >> 5;
    SPAN(0, 0); SPAN(0, 1);
    TSTAMPK(0, 0);
    asm volatile("griddepcontrol.launch_dependents;" ::: "memory");
    const bf16 pdt = in.logdt[d];
    const uint32_t pla = reinterpret_cast<const uint32_t*>(in.logA)[d * KG_THREADS + tid], pai = reinterpret_cast<const uint32_t*>(in.Aim)[d * KG_THREADS + tid];
    const uint32_t pcr = reinterpret_cast<const uint32_t*>(in.Cre)[d * KG_THREADS + tid], pci = reinterpret_cast<const uint32_t*>(in.Cim)[d * KG_THREADS + tid];
    const bf16* pfq = tid < 30 ? in.wqkv + (size_t)(d * 30 + tid) * 64 : tid < 40 ? in.wo + (size_t)(d * 10 + tid - 30) * 64 : in.x + (size_t)(d * 32 + tid - 40) * 64;
    if (tid < 72) asm volatile("prefetch.global.L2 [%0];" ::"l"(pfq));
    reinterpret_cast<uint4*>(E)[tid] = make_uint4(0, 0, 0, 0);
    if (tid < 32) reinterpret_cast<uint4*>(E)[96 + tid] = make_uint4(0, 0, 0, 0);
    const uint32_t tw = smem_u32(tab) + warp * 14336;
    const int g = lane >> 2, t = lane & 3;
    const uint32_t sta = tw + lane * 128 + ((2 * (lane & 3) + ((lane >> 2) & 1)) << 4);
    const uint32_t lda = tw + t * 128 + ((g ^ (2 * t)) << 4);
    const uint32_t stb = tw + 12288 + lane * 64 + ((4 * ((lane >> 1) & 1) + ((lane >> 2) & 3)) << 3);
    const uint32_t ldb = tw + 12288 + t * 64 + ((g ^ (4 * (t >> 1))) << 3);
    auto sts4 = [&](int e, int off, uint32_t a, uint32_t b, uint32_t c, uint32_t dd) {
        asm volatile("st.shared.v4.u32 [%0], {%1,%2,%3,%4};" ::"r"((sta ^ (e << 4)) + off), "r"(a), "r"(b), "r"(c), "r"(dd) : "memory");
    };
    auto lds4 = [&](int sp, int off, uint32_t* r) {
        asm volatile("ld.shared.v4.u32 {%0,%1,%2,%3}, [%4];" : "=r"(r[0]), "=r"(r[1]), "=r"(r[2]), "=r"(r[3]) : "r"((lda ^ ((sp & 1) << 4)) + sp * 512 + off) : "memory");
    };
    const float dt = rbf(expf(bf2f(pdt)));
    float2 C[2], y1[2], z8[2], y128[2];
    float cmax = 0.f;
#pragma unroll
    for (int m = 0; m < 2; m++) {
        const float wr2 = -rbf(expf(__uint_as_float(m ? pla & 0xffff0000u : pla << 16))) * dt * 1.4426950408889634f;
        const float wi = __uint_as_float(m ? pai & 0xffff0000u : pai << 16) * dt;
        C[m] = make_float2(__uint_as_float(m ? pcr & 0xffff0000u : pcr << 16) * dt, -__uint_as_float(m ? pci & 0xffff0000u : pci << 16) * dt);
        cmax = fmaxf(cmax, fmaxf(fabsf(C[m].x), fabsf(C[m].y)));
        y1[m] = cexp_at(wr2, -wi, 1.f); z8[m] = cexp_at(wr2, wi, 8.f); y128[m] = cexp_at(wr2, -wi, 128.f);
    }
    const int ex = min(max((int)(__reduce_max_sync(~0u, __float_as_uint(cmax)) >> 23), 20), 240);
    const float scale = __uint_as_float((uint32_t)(127 + 10 + 127 - ex) << 23), unscale = 2.0f * __uint_as_float((uint32_t)(ex - 10) << 23);
    TSTAMPK(4, 0);
    float k2048 = 0.f;
    {
        float2 h0[2], h1[2], g0[2], g1[2], g2[2], g2b[2], g3[2], g4[2], y2[2], y4[2];
#pragma unroll
        for (int m = 0; m < 2; m++) {
            h0[m] = make_float2(1.f, 0.f); h1[m] = csqr(csqr(csqr(z8[m])));
            g0[m] = make_float2(C[m].x * scale, C[m].y * scale);
            g1[m] = cmul(g0[m], y128[m]);
            const float2 y256 = csqr(y128[m]), y512 = csqr(y256);
            g2b[m] = g2[m] = cmul(g0[m], y256); g3[m] = cmul(g0[m], y512); g4[m] = cmul(g3[m], y512);
            y2[m] = csqr(y1[m]); y4[m] = csqr(y2[m]);
        }
#pragma unroll
        for (int e = 0; e < 8; e++) {
            sts4(e, 0, packh(h0[0]), packh(h1[0]), packh(h0[1]), packh(h1[1]));
            sts4(e, 4096, packh(g0[0]), packh(g0[1]), packh(g1[0]), packh(g1[1]));
            sts4(e, 8192, packh(g2[0]), packh(g2[1]), packh((e & 1) ? cmul(g3[0], y4[0]) : g3[0]), packh((e & 1) ? cmul(g3[1], y4[1]) : g3[1]));
            asm volatile("st.shared.v2.u32 [%0], {%1,%2};" ::"r"(stb ^ (e << 3)), "r"(packh(g4[0])), "r"(packh(g4[1])) : "memory");
#pragma unroll
            for (int m = 0; m < 2; m++) {
                if (e < 7) {
                    h0[m] = e ? cmul(h0[m], z8[m]) : z8[m]; h1[m] = cmul(h1[m], z8[m]); g0[m] = cmul(g0[m], y1[m]); g1[m] = cmul(g1[m], y1[m]);
                    g2[m] = e == 3 ? cmul(g2b[m], y128[m]) : cmul(g2[m], y2[m]);
                    if (e & 1) g3[m] = cmul(g3[m], y128[m]);
                    g4[m] = cmul(g4[m], y128[m]);
                } else k2048 += fmaf(g4[m].x, y128[m].x, -g4[m].y * y128[m].y);
            }
        }
    }
    TSTAMPK(6, 0);
    const int job = warp * DM + d;
    const bool isq = job < 1200;
    uint32_t sw[16];
    unsigned char* sdst = nullptr;
    int sn = 0;
    if (job < 1600) {
        const int j2 = isq ? job : job - 1200, kb = j2 % 10, col = (j2 / 10) * 16 + (lane >> 3) * 4;
        if (isq) {
            const int sec = col / DM, r = col - sec * DM, hg = r / 80;
            sn = hg * 160 + sec * 80 + r;
            sdst = reinterpret_cast<unsigned char*>(g_wq) + (hg * 9 + kb) * WQ_STAGE;
        } else {
            sn = col;
            sdst = reinterpret_cast<unsigned char*>(g_wo) + ((col / 80) * 9 + kb) * WO_STAGE;
        }
        const int pitch = isq ? 3 * DM : DM;
        const bf16* src = (isq ? in.wqkv : in.wo) + (size_t)(kb * 64 + (lane & 7) * 8) * pitch + col;
#pragma unroll
        for (int i = 0; i < 8; i++) {
            const uint2 v = __ldg(reinterpret_cast<const uint2*>(src + i * pitch));
            sw[2 * i] = v.x; sw[2 * i + 1] = v.y;
        }
        sn += kb << 16;
    } else if (job < 1600 + 64) {
        reinterpret_cast<uint4*>(g_sum)[(job - 1600) * 32 + lane] = make_uint4(0, 0, 0, 0);
    }
    __syncwarp();
    float acc[5][4];
#pragma unroll
    for (int j = 0; j < 5; j++)
#pragma unroll
        for (int k = 0; k < 4; k++) acc[j][k] = 0.f;
#pragma unroll
    for (int sp = 0; sp < 8; sp++) {
        uint32_t a[4], b[4], c[4], e0, e1;
        lds4(sp, 0, a); lds4(sp, 4096, b); lds4(sp, 8192, c);
        asm volatile("ld.shared.v2.u32 {%0,%1}, [%2];" : "=r"(e0), "=r"(e1) : "r"((ldb ^ ((sp & 3) << 3)) + sp * 256) : "memory");
        mma_f16(acc[0], a[0], a[1], a[2], a[3], b[0], b[1]);
        mma_f16(acc[1], a[0], a[1], a[2], a[3], b[2], b[3]);
        mma_f16(acc[2], a[0], a[1], a[2], a[3], c[0], c[1]);
        mma_f16(acc[3], a[0], a[1], a[2], a[3], c[2], c[3]);
        mma_f16(acc[4], a[0], a[1], a[2], a[3], e0, e1);
    }
#pragma unroll
    for (int o = 16; o; o >>= 1) k2048 += __shfl_xor_sync(~0u, k2048, o);
    __syncwarp();
    {
        float* Pp = reinterpret_cast<float*>(tab + warp * 896);
#pragma unroll
        for (int h = 0; h < 2; h++) {
            const int b = g + 8 * h;
            *reinterpret_cast<float2*>(Pp + 8 * b + 2 * t) = make_float2(acc[0][2 * h] * unscale, acc[0][2 * h + 1] * unscale);
            *reinterpret_cast<float2*>(Pp + 128 + 8 * b + 2 * t) = make_float2(acc[1][2 * h] * unscale, acc[1][2 * h + 1] * unscale);
            *reinterpret_cast<float2*>(Pp + 256 + 4 * b + 2 * (t & 1) + 64 * (t >> 1)) = make_float2(acc[2][2 * h] * unscale, acc[2][2 * h + 1] * unscale);
            *reinterpret_cast<float2*>(Pp + 384 + 2 * b + 32 * t) = make_float2(acc[3][2 * h] * unscale, acc[3][2 * h + 1] * unscale);
            Pp[512 + b + 32 * t] = acc[4][2 * h] * unscale;
            Pp[512 + b + 32 * t + 16] = acc[4][2 * h + 1] * unscale;
        }
        if (lane == 0) Pp[640] = k2048 * unscale;
    }
    TSTAMPK(7, 0);
    __syncthreads();
    TSTAMPK(9, 0);
    const float* Kp = reinterpret_cast<const float*>(tab);
    auto ksum = [&](int i) -> float { return (Kp[i] + Kp[3584 + i]) + Kp[7168 + i]; };
    auto ksum4 = [&](int q) -> float4 {
        const float4 a = reinterpret_cast<const float4*>(Kp)[q], b = reinterpret_cast<const float4*>(Kp)[896 + q], c = reinterpret_cast<const float4*>(Kp)[1792 + q];
        return make_float4((a.x + b.x) + c.x, (a.y + b.y) + c.y, (a.z + b.z) + c.z, (a.w + b.w) + c.w);
    };
    uint32_t* E2w = reinterpret_cast<uint32_t*>(E);
    {
        float4 v = ksum4(tid);
        if (tid == 95) v.w -= rbf(ksum(384));
        const uint32_t lo = pack2(v.x, v.y), hi = pack2(v.z, v.w);
        if (tid < 64) { E2w[9 + 2 * tid] = lo; E2w[10 + 2 * tid] = hi; }
        else {
            const int l = 256 + 8 * (tid - 64);
            if (tid > 64) E[18 + l - 1] = (unsigned short)lo;
            E2w[9 + l / 2] = __byte_perm(lo, 0, 0x1010);
            E2w[10 + l / 2] = __byte_perm(lo, hi, 0x5432);
            E2w[11 + l / 2] = __byte_perm(hi, 0, 0x1010);
            E[18 + l + 6] = (unsigned short)(hi >> 16);
        }
    }
    if (tid < 64) {
        float4 v = ksum4(96 + tid);
        if (tid == 31) v.w -= rbf(ksum(512));
        const int o = (tid < 32 ? 317 : 417 - 64) + 2 * tid;
        E2w[o] = pack2(v.x, v.y); E2w[o + 1] = pack2(v.z, v.w);
    } else if (tid == 88) E[800 + 34 + 128] = (unsigned short)(__float_as_uint(rbf(ksum(640))) >> 16);
    if (job < 1600) {
        const int c = lane & 7, n = sn & 0xffff;
#pragma unroll
        for (int q = 0; q < 4; q++) {
            uint32_t w[4];
#pragma unroll
            for (int j = 0; j < 4; j++) w[j] = __byte_perm(sw[4 * j + (q >> 1)], sw[4 * j + 2 + (q >> 1)], (q & 1) ? 0x7632 : 0x5410);
            *reinterpret_cast<uint4*>(sdst + (n + q) * 128 + ((c ^ ((n + q) & 7)) << 4)) = make_uint4(w[0], w[1], w[2], w[3]);
        }
    }
    __syncthreads();
    g_tap[d * 128 + tid] = reinterpret_cast<const uint4*>(E)[tid];
    if (tid < 32) g_tap[d * 128 + 96 + tid] = reinterpret_cast<const uint4*>(E)[96 + tid];
    TSTAMPK(10, 0);
    if (isq) {
        float4 a = make_float4(0.f, 0.f, 0.f, 0.f);
#pragma unroll
        for (int i = 0; i < 8; i++) {
            a.x += __uint_as_float(sw[2 * i] << 16); a.y += __uint_as_float(sw[2 * i] & 0xffff0000u);
            a.z += __uint_as_float(sw[2 * i + 1] << 16); a.w += __uint_as_float(sw[2 * i + 1] & 0xffff0000u);
        }
#pragma unroll
        for (int o = 1; o <= 4; o <<= 1) {
            a.x += __shfl_xor_sync(~0u, a.x, o); a.y += __shfl_xor_sync(~0u, a.y, o);
            a.z += __shfl_xor_sync(~0u, a.z, o); a.w += __shfl_xor_sync(~0u, a.w, o);
        }
        if ((lane & 7) == 0) *reinterpret_cast<float4*>(g_csp + (sn >> 16) * 1920 + (sn & 0xffff)) = a;
    }
    TSTAMPK(11, 0);
    SPAN(0, 3);
}

#define CV_MODE 0
#define CV_SLEEP 100
constexpr int CV_CPB = 5;
constexpr int CV_THREADS = 512;
constexpr int UPADF = 128;
constexpr int ULEN = UPADF + SEQ + 80;
constexpr int XLEN = SEQ + 16;
constexpr int BX_5 = 0, BX_3 = 3264, BX_9 = 6528, BX_7 = 8960, BX_LEN = 11392;
constexpr int CV_SM_T = 0;
constexpr int CV_SM_B = CV_CPB * TAPB;
constexpr int CV_SM_U = CV_SM_B + CV_CPB * BX_LEN;
constexpr int CV_SM_X = CV_SM_U + CV_CPB * ULEN * 2;
constexpr int CV_SM_Y = CV_SM_X + CV_CPB * XLEN * 2;
constexpr int CV_SM_P = CV_SM_Y + CV_CPB * XLEN * 2;
constexpr int CV_SM_CNT = CV_SM_P + 6 * 4096;
constexpr int CV_SM_O = (CV_SM_CNT + 128 + 127) & ~127;
constexpr int CV_SMEM = CV_SM_O + 20480;
static_assert(CV_SM_B % 128 == 0 && CV_SM_CNT % 16 == 0, "layout");

__device__ __forceinline__ void mma_bf16(float* d, uint32_t a0, uint32_t a1, uint32_t a2, uint32_t a3, uint32_t b0, uint32_t b1) {
    asm volatile("mma.sync.aligned.m16n8k16.row.col.f32.bf16.bf16.f32 {%0,%1,%2,%3}, {%4,%5,%6,%7}, {%8,%9}, {%0,%1,%2,%3};"
                 : "+f"(d[0]), "+f"(d[1]), "+f"(d[2]), "+f"(d[3]) : "r"(a0), "r"(a1), "r"(a2), "r"(a3), "r"(b0), "r"(b1));
}
__device__ __forceinline__ void mma_bf16_k8(float* d, uint32_t a0, uint32_t a1, uint32_t b0) {
    asm volatile("mma.sync.aligned.m16n8k8.row.col.f32.bf16.bf16.f32 {%0,%1,%2,%3}, {%4,%5}, {%6}, {%0,%1,%2,%3};"
                 : "+f"(d[0]), "+f"(d[1]), "+f"(d[2]), "+f"(d[3]) : "r"(a0), "r"(a1), "r"(b0));
}
__device__ __forceinline__ void ldsm_x4(uint32_t* r, uint32_t addr) {
    asm volatile("ldmatrix.sync.aligned.m8n8.x4.shared.b16 {%0,%1,%2,%3}, [%4];"
                 : "=r"(r[0]), "=r"(r[1]), "=r"(r[2]), "=r"(r[3]) : "r"(addr));
}

__device__ __forceinline__ void ldsm_x4_t(uint32_t* r, uint32_t addr) {
    asm volatile("ldmatrix.sync.aligned.m8n8.x4.trans.shared.b16 {%0,%1,%2,%3}, [%4];"
                 : "=r"(r[0]), "=r"(r[1]), "=r"(r[2]), "=r"(r[3]) : "r"(addr));
}
__device__ __forceinline__ uint32_t ln2(uint32_t x, uint32_t m, float ra, float rb) {
    const __nv_bfloat162 d = __hsub2(*reinterpret_cast<const __nv_bfloat162*>(&x), *reinterpret_cast<const __nv_bfloat162*>(&m));
    const uint32_t w = *reinterpret_cast<const uint32_t*>(&d);
    return pack2(__uint_as_float(w << 16) * ra, __uint_as_float(w & 0xffff0000u) * rb);
}
__device__ __forceinline__ void cp_async16(uint32_t dst, const void* src) {
    asm volatile("cp.async.cg.shared.global [%0], [%1], 16;" ::"r"(dst), "l"(src));
}
__device__ __forceinline__ void cp_async_wait_all() { asm volatile("cp.async.wait_all;" ::: "memory"); }

template <bool FULL>
__device__ __forceinline__ void direct_pass(float (&acc)[8][4], uint32_t ub, uint32_t o0, uint32_t o1, const uint2* __restrict__ Tp, bool first_half) {
    uint32_t sw[8][8];
#pragma unroll
    for (int j = 0; j < 8; j++) { ldsm_x4(&sw[j][0], ub + o0 + j * 256); ldsm_x4(&sw[j][4], ub + o1 + j * 256); }
#pragma unroll
    for (int M = 0; M < 4; M++) {
#pragma unroll
        for (int i = 0; i < 4; i++) {
            const uint2 hi = Tp[128 * M + 16 * i], lo = Tp[128 * M + 16 * i - 8];
#pragma unroll
            for (int j = FULL ? 0 : M; j < 8; j++) mma_bf16(acc[j], hi.x, hi.y, lo.x, lo.y, sw[(j - M) & 7][2 * i], sw[(j - M) & 7][2 * i + 1]);
        }
        if (FULL) {
            ldsm_x4(&sw[7 - M][0], ub + o0 - (M + 1) * 256);
            if (M < 3) ldsm_x4(&sw[7 - M][4], ub + o1 - (M + 1) * 256);
        }
    }
    if (first_half) {
        const uint2 hi = Tp[512], lo = Tp[504];
#pragma unroll
        for (int j = FULL ? 0 : 4; j < 8; j++) mma_bf16(acc[j], hi.x, hi.y, lo.x, lo.y, sw[(j - 4) & 7][0], sw[(j - 4) & 7][1]);
    }
}
__device__ __forceinline__ void mbar_init(uint32_t bar, int count) { asm volatile("mbarrier.init.shared::cta.b64 [%0], %1;" ::"r"(bar), "r"(count)); }
__device__ __forceinline__ void mbar_arrive(uint32_t bar) { asm volatile("mbarrier.arrive.shared::cta.b64 _, [%0];" ::"r"(bar) : "memory"); }
__device__ __forceinline__ void mbar_wait(uint32_t bar, uint32_t parity) {
    asm volatile("{\n.reg .pred p;\nWAIT_LOOP:\n"
                 "mbarrier.try_wait.parity.shared::cta.b64 p, [%0], %1;\n"
                 "@p bra.uni WAIT_DONE;\nbra.uni WAIT_LOOP;\nWAIT_DONE:\n}" ::"r"(bar), "r"(parity) : "memory");
}

__device__ __forceinline__ void mbar_expect_tx(uint32_t bar, uint32_t bytes) {
    asm volatile("mbarrier.arrive.expect_tx.shared::cta.b64 _, [%0], %1;" ::"r"(bar), "r"(bytes) : "memory");
}
__device__ __forceinline__ void tma_load_2d(uint32_t dst, const void* tmap, int c0, int c1, uint32_t bar) {
    asm volatile("cp.async.bulk.tensor.2d.shared::cluster.global.mbarrier::complete_tx::bytes [%0], [%1, {%3, %4}], [%2];"
                 ::"r"(dst), "l"(tmap), "r"(bar), "r"(c0), "r"(c1) : "memory");
}
__device__ __forceinline__ void fence_async_smem() { asm volatile("fence.proxy.async.shared::cta;" ::: "memory"); }
__device__ __forceinline__ void bulk_load(uint32_t dst, const void* src, uint32_t bytes, uint32_t bar) {
    asm volatile("cp.async.bulk.shared::cluster.global.mbarrier::complete_tx::bytes [%0], [%1], %2, [%3];"
                 ::"r"(dst), "l"(src), "r"(bytes), "r"(bar) : "memory");
}
__device__ __forceinline__ void tma_store_2d(const void* tmap, int c0, int c1, uint32_t src) {
    asm volatile("cp.async.bulk.tensor.2d.global.shared::cta.bulk_group [%0, {%1, %2}], [%3];" ::"l"(tmap), "r"(c0), "r"(c1), "r"(src) : "memory");
    asm volatile("cp.async.bulk.commit_group;" ::: "memory");
    asm volatile("cp.async.bulk.wait_group.read 0;" ::: "memory");
}
__device__ __forceinline__ void stsm_x4(uint32_t addr, uint32_t r0, uint32_t r1, uint32_t r2, uint32_t r3) {
    asm volatile("stmatrix.sync.aligned.m8n8.x4.shared.b16 [%0], {%1,%2,%3,%4};" ::"r"(addr), "r"(r0), "r"(r1), "r"(r2), "r"(r3) : "memory");
}
__device__ __forceinline__ void stsm_x4_t(uint32_t addr, uint32_t r0, uint32_t r1, uint32_t r2, uint32_t r3) {
    asm volatile("stmatrix.sync.aligned.m8n8.x4.trans.shared.b16 [%0], {%1,%2,%3,%4};" ::"r"(addr), "r"(r0), "r"(r1), "r"(r2), "r"(r3) : "memory");
}
__device__ __forceinline__ void prefetch_tmap(const void* tmap) { asm volatile("prefetch.tensormap [%0];" ::"l"(tmap) : "memory"); }

__device__ __forceinline__ uint32_t fin2(uint32_t x, uint32_t y, uint32_t u, uint32_t dk) {
    typedef __nv_bfloat162 b2;
    const b2 r = __hadd2_rn(*reinterpret_cast<const b2*>(&x), __hadd2_rn(*reinterpret_cast<const b2*>(&y),
                            __hmul2_rn(*reinterpret_cast<const b2*>(&u), *reinterpret_cast<const b2*>(&dk))));
    return *reinterpret_cast<const uint32_t*>(&r);
}
__global__ void __launch_bounds__(CV_THREADS, 1) conv_kernel(const bf16* __restrict__ Dskip, int layer, const __grid_constant__ CUtensorMap tmOut) {
    extern __shared__ __align__(128) unsigned char sm[];
    SPAN(3 + 4 * layer, 0);
    bf16* Us = reinterpret_cast<bf16*>(sm + CV_SM_U);
    bf16* Xs = reinterpret_cast<bf16*>(sm + CV_SM_X);
    bf16* Ys = reinterpret_cast<bf16*>(sm + CV_SM_Y);
    const int tid = threadIdx.x, lane = tid & 31, warp = tid >> 5;
    const int d0 = blockIdx.x * CV_CPB, tile = blockIdx.x; (void)tile;
    TSTAMP1X(9, 256);
    unsigned short dskr;
    asm volatile("ld.global.nc.u16 %0, [%1];" : "=h"(dskr) : "l"(Dskip + d0 + min(lane, CV_CPB - 1)));
    if (tid >= 256) {
        const int t2 = tid - 256;
        if (t2 == 0) {
            mbar_init(smem_u32(sm + CV_SM_CNT) + 104, 1);
            asm volatile("fence.mbarrier_init.release.cluster;" ::: "memory");
            mbar_expect_tx(smem_u32(sm + CV_SM_CNT) + 104, CV_CPB * 2048);
            bulk_load(smem_u32(sm + CV_SM_O), g_tap + d0 * 128, CV_CPB * 2048, smem_u32(sm + CV_SM_CNT) + 104);
        } else if (lane == 0) {
            mbar_init(smem_u32(sm + CV_SM_CNT) + 16 * (warp - 9), warp == 15 ? 16 : 1);
            if (warp < 15) mbar_init(smem_u32(sm + CV_SM_CNT) + 16 * (warp - 9) + 8, 1);
            else if (layer) prefetch_tmap(&tmOut);
        }
        if (t2 < 149) {
            const int k = t2;
            const int off = k < 18 ? BX_5 + 8 * k : k < 37 ? BX_3 + 8 * (k - 18) : k < 69 ? BX_9 + 8 * (k - 37) : k < 101 ? BX_7 + 8 * (k - 69)
                          : k < 133 ? 8 * (k - 101) : (UPADF + SEQ) * 2 + 8 * (k - 133);
#pragma unroll
            for (int c = 0; c < CV_CPB; c++) *reinterpret_cast<uint2*>(sm + (k < 101 ? CV_SM_B + c * BX_LEN : CV_SM_U + c * ULEN * 2) + off) = make_uint2(0, 0);
        }
        asm volatile("bar.sync 1, 256;" ::: "memory");
        TSTAMP1X(10, 256);
        mbar_wait(smem_u32(sm + CV_SM_CNT) + 104, 0);
        TSTAMP1X(11, 256);
#pragma unroll 1
        for (int r = t2; r < 392; r += 256) {
            const bool dd = r < 272, cc = r >= 368;
            const uint32_t* E2 = reinterpret_cast<const uint32_t*>(sm + CV_SM_O) + (dd ? r : r < 320 ? 300 + 2 * (r - 272) : cc ? 416 : 400 + 2 * (r - 320));
            const uint32_t* E3 = E2 + (dd ? 4 : cc ? 0 : 1);
            const uint32_t s0 = !cc ? 0x7610u : r == 382 ? 0x1044u : 0x4444u, s1 = !cc ? 0x7610u : r == 378 ? 0x1044u : 0x4444u;
            const uint32_t s2 = !cc ? 0x1032u : r == 381 ? 0x4410u : 0x4444u, s3 = !cc ? 0x1032u : r == 377 ? 0x4410u : 0x4444u;
            uint32_t w[CV_CPB][4];
#pragma unroll
            for (int c = 0; c < CV_CPB; c++) { w[c][0] = E2[512 * c]; w[c][1] = E2[512 * c + 1]; w[c][2] = E3[512 * c]; w[c][3] = E3[512 * c + 1]; }
#pragma unroll
            for (int c = 0; c < CV_CPB; c++) {
                const uint32_t a = __byte_perm(w[c][3], w[c][2], s1), b = __byte_perm(w[c][1], w[c][0], s2);
                *reinterpret_cast<uint4*>(sm + CV_SM_T + c * TAPB + r * 16) =
                    make_uint4(__byte_perm(w[c][1], w[c][0], s0), dd || cc ? a : b, dd || cc ? b : a, __byte_perm(w[c][3], w[c][2], s3));
            }
        }
        TSTAMP1X(12, 256);
        if (layer == 0) {
#pragma unroll
            for (int c = 0; c < CV_CPB; c++) reinterpret_cast<uint4*>(g_yT + (size_t)(d0 + c) * XCP)[t2] = make_uint4(~0u, ~0u, ~0u, ~0u);
        }
        pdl_sync();
        if (layer && blockIdx.x == 0 && t2 == 0) g_epoch = ld_epoch();
    } else {
        const uint4* ppv = reinterpret_cast<const uint4*>(g_piv + layer * SEQ) + tid;
        const float4* psv = reinterpret_cast<const float4*>(g_sum + layer * SEQ) + tid;
        const uint4* pxv = reinterpret_cast<const uint4*>(g_x1T + (size_t)d0 * XCP) + tid;
        asm volatile("" : "+l"(ppv), "+l"(psv), "+l"(pxv));
        pdl_sync();
        SPAN(3 + 4 * layer, 1);
        TSTAMP(0);
        if (threadIdx.x == 0) { GSTAMP(g_tim, 15); }
        float4 sv[4];
#pragma unroll
        for (int k = 0; k < 4; k++) sv[k] = __ldcg(psv + 256 * k);
        const uint4 pv = __ldcg(ppv);
        uint4 xv[CV_CPB];
#pragma unroll
        for (int c = 0; c < CV_CPB; c++) xv[c] = __ldcg(pxv + c * (XCP / 8));
        uint32_t mw[4];
        float rs[8];
#pragma unroll
        for (int k = 0; k < 4; k++) {
            const uint32_t pw = k == 0 ? pv.x : k == 1 ? pv.y : k == 2 ? pv.z : pv.w;
            const float d0_ = sv[k].x * (1.0f / DM), d1_ = sv[k].z * (1.0f / DM);
            mw[k] = pack2(__uint_as_float(pw << 16) + d0_, __uint_as_float(pw & 0xffff0000u) + d1_);
            const uint32_t vr = pack2(fmaxf(fmaf(-d0_, d0_, sv[k].y * (1.0f / DM)), 0.f), fmaxf(fmaf(-d1_, d1_, sv[k].w * (1.0f / DM)), 0.f));
            const uint32_t ve = pack2(__uint_as_float(vr << 16) + 1e-5f, __uint_as_float(vr & 0xffff0000u) + 1e-5f);
            const uint32_t sd = pack2(sqrt_apx(__uint_as_float(ve << 16)), sqrt_apx(__uint_as_float(ve & 0xffff0000u)));
            rs[2 * k] = rcp_apx(__uint_as_float(sd << 16)); rs[2 * k + 1] = rcp_apx(__uint_as_float(sd & 0xffff0000u));
        }
        if (rs[0] != 123.f) TSTAMP(13);
        const int ch = tid + UPADF / 8, pch = ch ^ ((ch >> 3) & 1);
#pragma unroll
        for (int c = 0; c < CV_CPB; c++) {
            *reinterpret_cast<uint4*>(Xs + c * XLEN + tid * 8) = xv[c];
            *reinterpret_cast<uint4*>(Us + c * ULEN + pch * 8) =
                make_uint4(ln2(xv[c].x, mw[0], rs[0], rs[1]), ln2(xv[c].y, mw[1], rs[2], rs[3]), ln2(xv[c].z, mw[2], rs[4], rs[5]), ln2(xv[c].w, mw[3], rs[6], rs[7]));
        }
    }
    __syncthreads();
    TSTAMP(1);
    const uint32_t rstart = warp < 8 ? (warp < 4 ? 0x02000000u : 0x06040000u) : (warp < 12 ? 0x0C0B0A08u : 0x1E1D150Fu);
    const uint32_t rcount = warp < 8 ? 0x02020000u : (warp < 12 ? 0x03010102u : 0x01010806u);
#pragma unroll 1
    for (int rd = (rstart >> (8 * (warp & 3))) & 0xff, re = rd + ((rcount >> (8 * (warp & 3))) & 0xff); rd < re; rd++) {
        const int i = 32 * rd + lane;
        if (i < CV_CPB * 193) {
            const int c = i / 193, chunk = i - c * 193 - 1, ch = chunk + UPADF / 8;
            const bf16* uc = Us + c * ULEN;
            const uint4 o = *reinterpret_cast<const uint4*>(uc + (ch ^ ((ch >> 3) & 1)) * 8);
            const uint2 lo = *reinterpret_cast<const uint2*>(uc + ((ch - 1) ^ (((ch - 1) >> 3) & 1)) * 8 + 4);
            const uint2 hi = *reinterpret_cast<const uint2*>(uc + ((ch + 1) ^ (((ch + 1) >> 3) & 1)) * 8);
            const uint32_t w[8] = {lo.x, lo.y, o.x, o.y, o.z, o.w, hi.x, hi.y};
            float v[16], b[8];
#pragma unroll
            for (int k = 0; k < 8; k++) { v[2 * k] = __uint_as_float(w[k] << 16); v[2 * k + 1] = __uint_as_float(w[k] & 0xffff0000u); }
            unsigned char* bx = sm + CV_SM_B + c * BX_LEN + chunk * 16;
#pragma unroll
            for (int k = 0; k < 8; k++) b[k] = v[k + 4] + (v[k + 3] + v[k + 5]);
            *reinterpret_cast<uint2*>(bx + BX_3 + 168) = make_uint2(pack2(b[0], b[1]), pack2(b[2], b[3]));
            *reinterpret_cast<uint2*>(bx + BX_3 + 176) = make_uint2(pack2(b[4], b[5]), pack2(b[6], b[7]));
#pragma unroll
            for (int k = 0; k < 8; k++) b[k] += v[k + 2] + v[k + 6];
            *reinterpret_cast<uint4*>(bx + BX_5 + 160) = make_uint4(pack2(b[0], b[1]), pack2(b[2], b[3]), pack2(b[4], b[5]), pack2(b[6], b[7]));
            if (chunk < 128) {
#pragma unroll
                for (int k = 0; k < 8; k++) b[k] += v[k + 1] + v[k + 7];
                *reinterpret_cast<uint4*>(bx + BX_7 + 272) = make_uint4(pack2(b[0], b[1]), pack2(b[2], b[3]), pack2(b[4], b[5]), pack2(b[6], b[7]));
#pragma unroll
                for (int k = 0; k < 8; k++) b[k] += v[k] + v[k + 8];
                *reinterpret_cast<uint4*>(bx + BX_9 + 272) = make_uint4(pack2(b[0], b[1]), pack2(b[2], b[3]), pack2(b[4], b[5]), pack2(b[6], b[7]));
            }
        }
    }
    __syncwarp();
    if (lane == 0) mbar_arrive(smem_u32(sm + CV_SM_CNT) + 96);
    TSTAMP(2);
    {
        const int g = lane >> 2, ti = lane & 3;
        const int e = g - 2 * ti;
        uint32_t lds_off[4];
        uint32_t off2, off3, offc;
        {
            const int mat = lane >> 3, r = lane & 7;
#pragma unroll
            for (int pr = 0; pr < 4; pr++) {
                const int iw = 2 * pr + (mat >> 1), half = mat & 1;
                const int chunk = (UPADF - 16 * iw + 16 * r + 8 * half) >> 3;
                lds_off[pr] = (uint32_t)((chunk ^ ((chunk >> 3) & 1)) * 16);
            }
            const int j2 = 13 + r + 8 * (mat >> 1), j3 = j2 + 2, i0 = 8 * (mat & 1);
            off2 = (j2 & 1) ? BX_3 + (4 * j2 + i0 + 84) * 2 : BX_5 + (4 * j2 + i0 + 80) * 2;
            off3 = ((j3 & 1) ? BX_7 : BX_9) + (8 * j3 + i0 + 136) * 2;
            const int cc = (UPADF + 16 * (r + (mat >> 1)) + i0) >> 3;
            offc = (uint32_t)((cc ^ ((cc >> 3) & 1)) * 16);
        }
        const uint32_t rtab = warp < 8 ? (warp < 4 ? 0x0B090200u : 0x0C0A0301u) : (warp < 12 ? 0x13111008u : 0x1412241Cu);
        const int rl = (rtab >> (8 * (warp & 3))) & 0xff, type = rl >> 3, c = rl & 7;
        const int H = (type == 1 || type == 2) ? 1 : 0, T0 = 8 * H;
        const uint2* Tc = reinterpret_cast<const uint2*>(sm + CV_SM_T + c * TAPB) + TPAD + e;
        const uint32_t ubase = smem_u32(Us + c * ULEN);
        const uint32_t bbase = smem_u32(sm + CV_SM_B + c * BX_LEN);
        float acc[8][4];
#pragma unroll
        for (int j = 0; j < 8; j++)
#pragma unroll
            for (int k = 0; k < 4; k++) acc[j][k] = 0.f;
#pragma unroll 1
        for (int pass = (type == 2 || type == 4) ? 1 : 0; pass < ((type == 1 || type == 3) ? 1 : 2); pass++) {
            const uint32_t o0 = pass ? lds_off[2] : lds_off[0], o1 = pass ? lds_off[3] : lds_off[1];
            if (H) direct_pass<true>(acc, ubase + T0 * 256, o0, o1, Tc + 64 * pass, pass == 0);
            else direct_pass<false>(acc, ubase, o0, o1, Tc + 64 * pass, pass == 0);
        }
        TSTAMP(6);
        mbar_wait(smem_u32(sm + CV_SM_CNT) + 96, 0);
        if (type != 1 && type != 4) {
            const uint32_t* w2 = reinterpret_cast<const uint32_t*>(sm + CV_SM_T + c * TAPB + TAP_W2) + (115 - 96) + 4 * g - 2 * ti;
            uint32_t f[10][2];
#pragma unroll
            for (int k = 0; k < 10; k++) { f[k][0] = w2[16 * k]; f[k][1] = w2[16 * k - 8]; }
            const uint32_t ab = bbase + off2 + (2 * T0 + 6) * 128;
            const int kmax = H ? 23 : 8;
            uint32_t a[3][4];
            ldsm_x4_t(a[0], ab);
            ldsm_x4_t(a[1], ab - 128);
#pragma unroll
            for (int kp = 0; kp < 24; kp++) {
                if (kp > kmax) break;
                if (kp < 22) ldsm_x4_t(a[(kp + 2) % 3], ab - min(kp + 2, kmax) * 128);
#pragma unroll
                for (int j = 0; j < 8; j++) {
                    const int ee = 2 * j - 14 + kp;
                    if (ee >= 0 && ee <= 9) mma_bf16(acc[j], a[kp % 3][0], a[kp % 3][1], a[kp % 3][2], a[kp % 3][3], f[ee][0], f[ee][1]);
                }
            }
        }
        TSTAMP(7);
        if (type != 2 && type != 4) {
            const uint32_t* w3 = reinterpret_cast<const uint32_t*>(sm + CV_SM_T + c * TAPB + TAP_W3) + (129 - 96) + 2 * (g - ti);
            uint32_t f[9][2];
#pragma unroll
            for (int k = 0; k < 9; k++) { f[k][0] = w3[16 * k]; f[k][1] = w3[16 * k - 8]; }
            const uint32_t ab = bbase + off3 + (T0 - 2) * 256;
            uint32_t a[3][4];
            ldsm_x4_t(a[0], ab);
            ldsm_x4_t(a[1], ab - H * 256);
#pragma unroll
            for (int kp = 0; kp < 9; kp++) {
                if (kp > T0) break;
                if (kp < 7) ldsm_x4_t(a[(kp + 2) % 3], ab - min(kp + 2, T0) * 256);
#pragma unroll
                for (int j = 0; j < 8; j++) {
                    const int dl = j - 7 + kp;
                    if (dl >= 0 && dl <= 8) mma_bf16(acc[j], a[kp % 3][0], a[kp % 3][1], a[kp % 3][2], a[kp % 3][3], f[dl][0], f[dl][1]);
                }
            }
            const uint2* Dc = reinterpret_cast<const uint2*>(sm + CV_SM_T + c * TAPB + TAP_C) + e;
            const uint2 h63 = Dc[16], h64 = Dc[32], l63 = Dc[8], l64 = Dc[24];
#pragma unroll
            for (int j = 0; j < 8; j++)
                if (j == 7 || H) {
                    uint32_t bq[4];
                    ldsm_x4(bq, ubase + offc + (T0 + j - 8) * 256);
                    mma_bf16(acc[j], h64.x, h64.y, l64.x, l64.y, bq[0], bq[1]);
                    mma_bf16(acc[j], h63.x, h63.y, l63.x, l63.y, bq[2], bq[3]);
                }
        }
        TSTAMP(8);
        const bool hi_half = (type == 2 || type == 4);
        if (type != 0) {
            const int pair = H ? c : 5;
            float4* give = reinterpret_cast<float4*>(sm + CV_SM_P + pair * 4096 + (hi_half ? 2048 : 0)) + lane;
            const float4* take = reinterpret_cast<const float4*>(sm + CV_SM_P + pair * 4096 + (hi_half ? 0 : 2048)) + lane;
            const uint32_t pb = smem_u32(sm + CV_SM_CNT) + pair * 16;
#pragma unroll
            for (int j = 0; j < 4; j++)
                give[32 * j] = hi_half ? make_float4(acc[j][0], acc[j][1], acc[j][2], acc[j][3]) : make_float4(acc[j + 4][0], acc[j + 4][1], acc[j + 4][2], acc[j + 4][3]);
            __syncwarp();
            if (lane == 0) mbar_arrive(pb + (hi_half ? 8 : 0));
            mbar_wait(pb + (hi_half ? 0 : 8), 0);
#pragma unroll
            for (int j = 0; j < 4; j++) {
                const float4 v = take[32 * j];
                acc[j][0] = (hi_half ? acc[j + 4][0] : acc[j][0]) + v.x; acc[j][1] = (hi_half ? acc[j + 4][1] : acc[j][1]) + v.y;
                acc[j][2] = (hi_half ? acc[j + 4][2] : acc[j][2]) + v.z; acc[j][3] = (hi_half ? acc[j + 4][3] : acc[j][3]) + v.w;
            }
        }
        const uint32_t dk = __shfl_sync(~0u, (uint32_t)dskr, c) * 0x10001u;
#pragma unroll 1
        for (int rnd = 0; rnd < (type == 0 ? 2 : 1); rnd++) {
            const int Q = 2 * H + (hi_half ? 1 : rnd);
            if (rnd) {
#pragma unroll
                for (int j = 0; j < 4; j++)
#pragma unroll
                    for (int k = 0; k < 4; k++) acc[j][k] = acc[j + 4][k];
            }
            const uint32_t ya = smem_u32(Ys + c * XLEN) + (128 * (4 * Q + (lane >> 4)) + 16 * (lane & 7) + 8 * ((lane >> 3) & 1)) * 2;
#pragma unroll
            for (int j = 0; j < 4; j += 2)
                asm volatile("stmatrix.sync.aligned.m8n8.x4.trans.shared.b16 [%0], {%1,%2,%3,%4};" ::"r"(ya + j * 256),
                             "r"(pack2(acc[j][0], acc[j][1])), "r"(pack2(acc[j][2], acc[j][3])),
                             "r"(pack2(acc[j + 1][0], acc[j + 1][1])), "r"(pack2(acc[j + 1][2], acc[j + 1][3])) : "memory");
            __syncwarp();
            uint4 yv[2], xv[2], uv[2];
#pragma unroll
            for (int k = 0; k < 2; k++) {
                const int t = 512 * Q + 256 * k + 8 * lane, cu = (t + UPADF) >> 3;
                yv[k] = *reinterpret_cast<const uint4*>(Ys + c * XLEN + t);
                xv[k] = *reinterpret_cast<const uint4*>(Xs + c * XLEN + t);
                uv[k] = *reinterpret_cast<const uint4*>(Us + c * ULEN + (cu ^ ((cu >> 3) & 1)) * 8);
            }
#pragma unroll
            for (int k = 0; k < 2; k++)
                asm volatile("st.relaxed.gpu.global.v4.u32 [%0], {%1,%2,%3,%4};" ::"l"((layer ? g_yT : g_xcT) + (size_t)(d0 + c) * XCP + 512 * Q + 256 * k + 8 * lane),
                             "r"(fin2(xv[k].x, yv[k].x, uv[k].x, dk)), "r"(fin2(xv[k].y, yv[k].y, uv[k].y, dk)), "r"(fin2(xv[k].z, yv[k].z, uv[k].z, dk)), "r"(fin2(xv[k].w, yv[k].w, uv[k].w, dk)) : "memory");
        }
        TSTAMP(4);
        if (layer == 1) {
            const int mb = blockIdx.x >> 3, cg = blockIdx.x & 7;
            const bf16* src = g_yT + (size_t)(cg * 80 + (tid >> 4)) * XCP + mb * 128 + (tid & 15) * 8;
            uint32_t v[3][4];
            __syncthreads();
            TSTAMP(5);
            uint32_t todo = warp < 8 ? 7 : 3;
#pragma unroll 1
            for (int it = 0; it < SPIN_MAX; it++) {
#pragma unroll
                for (int k = 0; k < 3; k++)
                    if (todo >> k & 1)
                        asm volatile("ld.relaxed.gpu.global.v4.u32 {%0,%1,%2,%3}, [%4];" : "=r"(v[k][0]), "=r"(v[k][1]), "=r"(v[k][2]), "=r"(v[k][3]) : "l"(src + k * (32 * XCP)) : "memory");
#pragma unroll
                for (int k = 0; k < 3; k++)
                    if ((todo >> k & 1) && v[k][0] != ~0u && v[k][1] != ~0u && v[k][2] != ~0u && v[k][3] != ~0u) {
                        *reinterpret_cast<uint4*>(sm + (32 * k + (tid >> 4)) * 272 + (tid & 15) * 16) = make_uint4(v[k][0], v[k][1], v[k][2], v[k][3]);
                        todo ^= 1u << k;
                    }
                if (!todo) break;
                __nanosleep(CV_SLEEP);
            }
            __syncthreads();
            uint32_t w[12];
#pragma unroll
            for (int k = 0; k < 3; k++) ldsm_x4(&w[4 * k], smem_u32(sm) + min(32 * k + lane, 79) * 272 + warp * 16);
            const uint32_t ot = smem_u32(sm + CV_SM_O) + warp * 1280, oa = ot + (lane & 7) * 160 + (lane >> 3) * 16;
            stsm_x4_t(oa, w[0], w[1], w[2], w[3]);
            stsm_x4_t(oa + 64, w[4], w[5], w[6], w[7]);
            asm volatile("stmatrix.sync.aligned.m8n8.x2.trans.shared.b16 [%0], {%1,%2};" ::"r"(oa + 128), "r"(w[8]), "r"(w[9]) : "memory");
            fence_async_smem();
            __syncwarp();
            if (lane == 0) tma_store_2d(&tmOut, cg * 80, mb * 128 + 8 * warp, ot);
        }
    }
    TSTAMP(3);
    GSTAMP(g_tim, 14);
    SPAN(3 + 4 * layer, 3);
}

__device__ __forceinline__ void wgmma_fence() { asm volatile("wgmma.fence.sync.aligned;" ::: "memory"); }
__device__ __forceinline__ void wgmma_commit() { asm volatile("wgmma.commit_group.sync.aligned;" ::: "memory"); }
template <int N> __device__ __forceinline__ void wgmma_wait() { asm volatile("wgmma.wait_group.sync.aligned %0;" ::"n"(N) : "memory"); }
__device__ __forceinline__ uint64_t make_desc(uint32_t addr, uint32_t lbo, uint32_t sbo, uint32_t mode) {
    return (uint64_t)((addr & 0x3FFFF) >> 4) | ((uint64_t)(lbo >> 4) << 16) | ((uint64_t)(sbo >> 4) << 32) | ((uint64_t)mode << 62);
}
template <int TA, int TB>
__device__ __forceinline__ void wgmma_n240(float (&d)[120], uint64_t da, uint64_t db) {
    asm volatile("wgmma.mma_async.sync.aligned.m64n240k16.f32.bf16.bf16 {%0,%1,%2,%3,%4,%5,%6,%7,%8,%9,%10,%11,%12,%13,%14,%15,%16,%17,%18,%19,%20,%21,%22,%23,%24,%25,%26,%27,%28,%29,%30,%31,%32,%33,%34,%35,%36,%37,%38,%39,%40,%41,%42,%43,%44,%45,%46,%47,%48,%49,%50,%51,%52,%53,%54,%55,%56,%57,%58,%59,%60,%61,%62,%63,%64,%65,%66,%67,%68,%69,%70,%71,%72,%73,%74,%75,%76,%77,%78,%79,%80,%81,%82,%83,%84,%85,%86,%87,%88,%89,%90,%91,%92,%93,%94,%95,%96,%97,%98,%99,%100,%101,%102,%103,%104,%105,%106,%107,%108,%109,%110,%111,%112,%113,%114,%115,%116,%117,%118,%119}, %120, %121, 1, 1, 1, %122, %123;"
                 : "+f"(d[0]), "+f"(d[1]), "+f"(d[2]), "+f"(d[3]), "+f"(d[4]), "+f"(d[5]), "+f"(d[6]), "+f"(d[7]), "+f"(d[8]), "+f"(d[9]), "+f"(d[10]), "+f"(d[11]), "+f"(d[12]), "+f"(d[13]), "+f"(d[14]), "+f"(d[15]), "+f"(d[16]), "+f"(d[17]), "+f"(d[18]), "+f"(d[19]), "+f"(d[20]), "+f"(d[21]), "+f"(d[22]), "+f"(d[23]), "+f"(d[24]), "+f"(d[25]), "+f"(d[26]), "+f"(d[27]), "+f"(d[28]), "+f"(d[29]), "+f"(d[30]), "+f"(d[31]), "+f"(d[32]), "+f"(d[33]), "+f"(d[34]), "+f"(d[35]), "+f"(d[36]), "+f"(d[37]), "+f"(d[38]), "+f"(d[39]), "+f"(d[40]), "+f"(d[41]), "+f"(d[42]), "+f"(d[43]), "+f"(d[44]), "+f"(d[45]), "+f"(d[46]), "+f"(d[47]), "+f"(d[48]), "+f"(d[49]), "+f"(d[50]), "+f"(d[51]), "+f"(d[52]), "+f"(d[53]), "+f"(d[54]), "+f"(d[55]), "+f"(d[56]), "+f"(d[57]), "+f"(d[58]), "+f"(d[59]), "+f"(d[60]), "+f"(d[61]), "+f"(d[62]), "+f"(d[63]), "+f"(d[64]), "+f"(d[65]), "+f"(d[66]), "+f"(d[67]), "+f"(d[68]), "+f"(d[69]), "+f"(d[70]), "+f"(d[71]), "+f"(d[72]), "+f"(d[73]), "+f"(d[74]), "+f"(d[75]), "+f"(d[76]), "+f"(d[77]), "+f"(d[78]), "+f"(d[79]), "+f"(d[80]), "+f"(d[81]), "+f"(d[82]), "+f"(d[83]), "+f"(d[84]), "+f"(d[85]), "+f"(d[86]), "+f"(d[87]), "+f"(d[88]), "+f"(d[89]), "+f"(d[90]), "+f"(d[91]), "+f"(d[92]), "+f"(d[93]), "+f"(d[94]), "+f"(d[95]), "+f"(d[96]), "+f"(d[97]), "+f"(d[98]), "+f"(d[99]), "+f"(d[100]), "+f"(d[101]), "+f"(d[102]), "+f"(d[103]), "+f"(d[104]), "+f"(d[105]), "+f"(d[106]), "+f"(d[107]), "+f"(d[108]), "+f"(d[109]), "+f"(d[110]), "+f"(d[111]), "+f"(d[112]), "+f"(d[113]), "+f"(d[114]), "+f"(d[115]), "+f"(d[116]), "+f"(d[117]), "+f"(d[118]), "+f"(d[119])
                 : "l"(da), "l"(db), "n"(TA), "n"(TB));
}

template <int TA, int TB>
__device__ __forceinline__ void wgmma_n80(float (&d)[40], uint64_t da, uint64_t db) {
    asm volatile("wgmma.mma_async.sync.aligned.m64n80k16.f32.bf16.bf16 {%0,%1,%2,%3,%4,%5,%6,%7,%8,%9,%10,%11,%12,%13,%14,%15,%16,%17,%18,%19,%20,%21,%22,%23,%24,%25,%26,%27,%28,%29,%30,%31,%32,%33,%34,%35,%36,%37,%38,%39}, %40, %41, 1, 1, 1, %42, %43;"
                 : "+f"(d[0]), "+f"(d[1]), "+f"(d[2]), "+f"(d[3]), "+f"(d[4]), "+f"(d[5]), "+f"(d[6]), "+f"(d[7]), "+f"(d[8]), "+f"(d[9]), "+f"(d[10]), "+f"(d[11]), "+f"(d[12]), "+f"(d[13]), "+f"(d[14]), "+f"(d[15]), "+f"(d[16]), "+f"(d[17]), "+f"(d[18]), "+f"(d[19]), "+f"(d[20]), "+f"(d[21]), "+f"(d[22]), "+f"(d[23]), "+f"(d[24]), "+f"(d[25]), "+f"(d[26]), "+f"(d[27]), "+f"(d[28]), "+f"(d[29]), "+f"(d[30]), "+f"(d[31]), "+f"(d[32]), "+f"(d[33]), "+f"(d[34]), "+f"(d[35]), "+f"(d[36]), "+f"(d[37]), "+f"(d[38]), "+f"(d[39])
                 : "l"(da), "l"(db), "n"(TA), "n"(TB));
}

constexpr int A1_THREADS = 384;
constexpr int A1_NST = 4;
#define A1_PRE0 2
#define A1_SDELAY 1
#define A1_PRE1 1
constexpr int A1_STAGE = 16384 + WQ_STAGE;
constexpr int A1_KVP = 336;
constexpr int A1_SM_KV = 2 * A1_STAGE;
constexpr int A1_SM_O = A1_SM_KV + 144 * A1_KVP;
constexpr int A1_SM_R = A1_NST * A1_STAGE;
constexpr int A1_SM_BAR = A1_SM_R + 20480;
constexpr int A1_SM_CS = A1_SM_BAR + 256;
constexpr int A1_SM_RS = A1_SM_CS + 1024;
constexpr int A1_SM_RED = A1_SM_RS + 1024;
constexpr int A1_SMEM = A1_SM_RED + 1152 + 1024;
static_assert(A1_SM_O % 128 == 0 && A1_SM_O + 20480 <= A1_SM_R, "layout");

template <int L>
__device__ __forceinline__ void a1_mainloop(float (&acc)[120], uint32_t sbase, uint32_t bars, int tile) {
    const int wg = threadIdx.x >> 7;
    constexpr int layer = L; (void)layer;
#pragma unroll 1
    for (int t = 0; t < 10; t++) {
        const int st = t % A1_NST;
        mbar_wait(bars + 8 * st, (t / A1_NST) & 1);
        TSTAMP3(1 + t);
        const uint32_t sa = sbase + st * A1_STAGE;
        wgmma_fence();
#pragma unroll
        for (int kk = 0; kk < 4; kk++)
            wgmma_n240<L, 0>(acc, L ? make_desc(sa + wg * 8192 + kk * 2048, 8192, 1024, 1) : make_desc(sa + wg * 8192 + kk * 32, 16, 1024, 1), make_desc(sa + 16384 + kk * 32, 16, 1024, 1));
        wgmma_commit();
        wgmma_wait<1>();
        if (t > 0 && (threadIdx.x & 127) == 0) mbar_arrive(t < 9 ? bars + 8 * (A1_NST + (t - 1) % A1_NST) : bars + 144);
    }
}

__global__ void __launch_bounds__(A1_THREADS, 1) a1_kernel(const int layer, const bf16* __restrict__ x0, const __grid_constant__ CUtensorMap tmX,
                                                           const __grid_constant__ CUtensorMap tmR, const __grid_constant__ CUtensorMap tmOst) {
    extern __shared__ unsigned char smraw[];
    const uint32_t sbase = (smem_u32(smraw) + 1023) & ~1023u;
    const uint32_t bars = sbase + A1_SM_BAR;
    const uint32_t bar_stat = bars + 64, bar_kv = bars + 72, bar_r = bars + 152;
    const int tid = threadIdx.x, wg = tid >> 7;
    SPAN(1 + 4 * layer, 0);
    const int tile = sm_tile(2 * layer);
    if (tile >= 128) return;
    const int mb = (tile >> 2) & 15, hg = 4 * (tile >> 6) + (tile & 3);
    const uint32_t tag = ld_epoch();
    unsigned char* stg = smraw + (sbase - smem_u32(smraw));
    float* cs = reinterpret_cast<float*>(stg + A1_SM_CS);
    float2* rst = reinterpret_cast<float2*>(stg + A1_SM_RS);
    if ((tid & 31) == 0 && tid < 320) {
        const int w = tid >> 5;
        mbar_init(bars + 16 * w, w < 2 ? 1 : w < 4 ? 2 : w == 4 ? 4 : w == 9 ? 2 : 1);
        mbar_init(bars + 16 * w + 8, w < 2 ? 1 : w < 4 ? 2 : w == 4 ? 4 : 1);
        if (w < 2) { mbar_expect_tx(bars + 16 * w, A1_STAGE); mbar_expect_tx(bars + 16 * w + 8, A1_STAGE); }
        if (w == 9) mbar_expect_tx(bar_r, 20480);
        asm volatile("fence.mbarrier_init.release.cluster;" ::: "memory");
    } else if (tid == 320) { prefetch_tmap(&tmX); prefetch_tmap(&tmR); prefetch_tmap(&tmOst); }
    __syncthreads();
    if (wg == 2) {
        const bool is_producer = (tid == 256);
        const int t = tid - 256, pre = layer ? A1_PRE1 : A1_PRE0;
        auto issue_w = [&](int kb) {
            bulk_load(sbase + (kb % A1_NST) * A1_STAGE + 16384, reinterpret_cast<const unsigned char*>(g_wq) + (hg * 10 + kb) * WQ_STAGE, WQ_STAGE, bars + 8 * (kb % A1_NST));
        };
        auto issue_x = [&](int kb) {
            const uint32_t dst = sbase + (kb % A1_NST) * A1_STAGE, full = bars + 8 * (kb % A1_NST);
            if (layer == 0) tma_load_2d(dst, &tmX, kb * 64, mb * 128, full);
            else { tma_load_2d(dst, &tmX, mb * 128, kb * 64, full); tma_load_2d(dst + 8192, &tmX, mb * 128 + 64, kb * 64, full); }
        };
        if (is_producer) {
            for (int kb = 0; kb < pre; kb++) { if (layer) issue_w(kb); else issue_x(kb); }
        }
        if (layer || tid < 288) pdl_sync();
        if (is_producer) {
            for (int kb = 0; kb < A1_NST; kb++) {
                if (kb == A1_SDELAY && layer) {
                    tma_load_2d(sbase + A1_SM_R, &tmR, mb * 128, hg * 80, bar_r); tma_load_2d(sbase + A1_SM_R + 10240, &tmR, mb * 128 + 64, hg * 80, bar_r);
                }
                if (kb >= pre || layer) issue_x(kb);
                if (kb >= pre || !layer) issue_w(kb);
            }
        }
        if (tid >= 288) {
            const int j = tid - 288;
            if (layer == 0) {
                float* red = reinterpret_cast<float*>(stg + A1_SM_RED);
                const int r = j / 6, c6 = j - 6 * r;
                const uint4* src = reinterpret_cast<const uint4*>(x0 + (size_t)(mb * 128 + hg * 16 + r) * DM);
                uint4 v[14];
#pragma unroll
                for (int k = 0; k < 14; k++) v[k] = __ldg(src + min(c6 + 6 * k, 79));
                const float p0 = __uint_as_float(__ldg(reinterpret_cast<const uint32_t*>(src)) << 16);
                float s[2] = {0.f, 0.f}, q[2] = {0.f, 0.f};
#pragma unroll
                for (int k = 0; k < 14; k++) {
                    const uint32_t w[4] = {v[k].x, v[k].y, v[k].z, v[k].w};
                    if (k < 13 || c6 < 2) {
#pragma unroll
                        for (int i = 0; i < 4; i++) {
                            const float a = __uint_as_float(w[i] << 16) - p0, b = __uint_as_float(w[i] & 0xffff0000u) - p0;
                            s[0] += a; s[1] += b; q[0] = fmaf(a, a, q[0]); q[1] = fmaf(b, b, q[1]);
                        }
                    }
                }
                red[j] = s[0] + s[1]; red[96 + j] = q[0] + q[1]; red[192 + j] = p0;
                asm volatile("bar.sync 2, 96;" ::: "memory");
                if (j < 16) {
                    float s0 = 0.f, q0 = 0.f;
#pragma unroll
                    for (int k = 0; k < 6; k++) { s0 += red[6 * j + k]; q0 += red[96 + 6 * j + k]; }
                    const float d = s0 * (1.0f / DM);
                    const uint32_t ms = pack2(red[192 + 6 * j] + d, rbf(sqrtf(rbf(rbf(fmaxf(fmaf(-d, d, q0 * (1.0f / DM)), 0.f)) + 1e-5f))));
                    asm volatile("st.global.cg.u64 [%0], %1;" ::"l"(g_rstat + mb * 128 + hg * 16 + j), "l"(tagw(ms, tag)) : "memory");
                    g_piv[mb * 128 + hg * 16 + j] = __ushort_as_bfloat16((unsigned short)ms);
                }
                pdl_sync();
            } else if (j >= 32) {
                const int ch = j & 7, kg = (j >> 3) & 3;
                const unsigned char* src = stg + A1_SM_R + ((j >> 5) - 1) * 10240;
                mbar_wait(bar_r, 0);
                uint4 v[20];
#pragma unroll
                for (int k = 0; k < 20; k++) v[k] = *reinterpret_cast<const uint4*>(src + (4 * k + kg) * 128 + ((ch ^ ((4 * k + kg) & 7)) << 4));
                const uint4 pv = *reinterpret_cast<const uint4*>(src + (ch << 4));
                float s[8], q[8], p0[8] = {__uint_as_float(pv.x << 16), __uint_as_float(pv.x & 0xffff0000u), __uint_as_float(pv.y << 16), __uint_as_float(pv.y & 0xffff0000u),
                                           __uint_as_float(pv.z << 16), __uint_as_float(pv.z & 0xffff0000u), __uint_as_float(pv.w << 16), __uint_as_float(pv.w & 0xffff0000u)};
#pragma unroll
                for (int i = 0; i < 8; i++) { s[i] = 0.f; q[i] = 0.f; }
#pragma unroll
                for (int k = 0; k < 20; k++) {
                    const uint32_t w[4] = {v[k].x, v[k].y, v[k].z, v[k].w};
#pragma unroll
                    for (int i = 0; i < 4; i++) {
                        const float a = __uint_as_float(w[i] << 16) - p0[2 * i], b = __uint_as_float(w[i] & 0xffff0000u) - p0[2 * i + 1];
                        s[2 * i] += a; s[2 * i + 1] += b; q[2 * i] = fmaf(a, a, q[2 * i]); q[2 * i + 1] = fmaf(b, b, q[2 * i + 1]);
                    }
                }
#pragma unroll
                for (int i = 0; i < 4; i++) {
                    const bool up = kg & 2;
                    const float ss = __shfl_xor_sync(~0u, up ? s[i] : s[i + 4], 16), qq = __shfl_xor_sync(~0u, up ? q[i] : q[i + 4], 16);
                    s[i] = (up ? s[i + 4] : s[i]) + ss; q[i] = (up ? q[i + 4] : q[i]) + qq; p0[i] = up ? p0[i + 4] : p0[i];
                }
#pragma unroll
                for (int i = 0; i < 2; i++) {
                    const bool up = kg & 1;
                    const float ss = __shfl_xor_sync(~0u, up ? s[i] : s[i + 2], 8), qq = __shfl_xor_sync(~0u, up ? q[i] : q[i + 2], 8);
                    s[i] = (up ? s[i + 2] : s[i]) + ss; q[i] = (up ? q[i + 2] : q[i]) + qq; p0[i] = up ? p0[i + 2] : p0[i];
                }
#pragma unroll
                for (int r = 0; r < 2; r++) {
                    const float d = s[r] * (1.0f / 80.0f);
                    st_tag2(g_part + (mb * 8 + hg) * 128 + 64 * r + j - 32, __float_as_uint(p0[r] + d), __float_as_uint(fmaxf(fmaf(-d, s[r], q[r]), 0.f)), tag);
                }
            }
            TSTAMP1T(12, 320);
            if (j < 32) {
#pragma unroll
                for (int h = 0; h < 2; h++) {
                    const int i = j + 32 * h;
                    if (i < 60) {
                        float4 a = make_float4(0.f, 0.f, 0.f, 0.f);
#pragma unroll
                        for (int k = 0; k < 10; k++) {
                            const float4 v = __ldcg(reinterpret_cast<const float4*>(g_csp + k * 1920 + hg * 240) + i);
                            a.x += v.x; a.y += v.y; a.z += v.z; a.w += v.w;
                        }
                        reinterpret_cast<float4*>(cs)[i] = a;
                    }
                }
                TSTAMP1T(13, 288);
            } else if (layer == 0) {
                ulonglong2 v;
#pragma unroll 1
                for (int it = 0; it < SPIN_MAX; it++) {
                    v = ld_tag2(reinterpret_cast<const ulonglong2*>(g_rstat + mb * 128) + j - 32);
                    if (tag_ok(v, tag)) break;
                    __nanosleep(100);
                }
                *reinterpret_cast<float4*>(rst + 2 * (j - 32)) = make_float4(__uint_as_float((uint32_t)v.x << 16), __frcp_rn(__uint_as_float((uint32_t)v.x & 0xffff0000u)),
                                                                             __uint_as_float((uint32_t)v.y << 16), __frcp_rn(__uint_as_float((uint32_t)v.y & 0xffff0000u)));
            } else {
                const ulonglong2* gp = g_part + mb * 8 * 128 + j - 32;
#pragma unroll 1
                for (int it = 0; it < SPIN_MAX; it++) {
                    if (__all_sync(~0u, tag_ok(ld_tag2(gp + (j & 7) * 128 + 64), tag))) break;
                    __nanosleep(200);
                }
                ulonglong2 pv[16];
#pragma unroll 1
                for (int it = 0; it < SPIN_MAX; it++) {
                    bool ok = true;
#pragma unroll
                    for (int k = 0; k < 16; k++) pv[k] = ld_tag2(gp + k * 64);
#pragma unroll
                    for (int k = 0; k < 16; k++) ok = ok && tag_ok(pv[k], tag);
                    if (ok) break;
                    __nanosleep(200);
                }
                float o[4];
#pragma unroll
                for (int r = 0; r < 2; r++) {
                    float mean = 0.f, m2 = 0.f;
#pragma unroll
                    for (int k = 0; k < 8; k++) mean += __uint_as_float((uint32_t)pv[2 * k + r].x);
                    mean *= 0.125f;
#pragma unroll
                    for (int k = 0; k < 8; k++) {
                        const float dm = __uint_as_float((uint32_t)pv[2 * k + r].x) - mean;
                        m2 += fmaf(80.0f * dm, dm, __uint_as_float((uint32_t)pv[2 * k + r].y));
                    }
                    o[2 * r] = rbf(mean);
                    o[2 * r + 1] = __frcp_rn(rbf(sqrtf(rbf(rbf(m2 * (1.0f / DM)) + 1e-5f))));
                }
                const int row = ((j >> 5) - 1) * 64 + (j & 7) * 8 + ((j >> 3) & 3) * 2;
                *reinterpret_cast<float4*>(rst + row) = make_float4(o[0], o[1], o[2], o[3]);
                if (hg == 0) *reinterpret_cast<uint32_t*>(g_piv + SEQ + mb * 128 + row) = __byte_perm(__float_as_uint(o[0]), __float_as_uint(o[2]), 0x7632);
            }
            TSTAMP1T(7, 320);
        } else if (is_producer) {
            for (int kb = A1_NST; kb < 10; kb++) {
                mbar_wait(bars + 8 * (A1_NST + kb % A1_NST), ((kb / A1_NST) - 1) & 1);
                mbar_expect_tx(bars + 8 * (kb % A1_NST), A1_STAGE);
                issue_x(kb); issue_w(kb);
            }
            TSTAMP1T(6, 256);
        }
        __syncwarp();
        if ((tid & 31) == 0) mbar_arrive(bar_stat);
        mbar_wait(bars + 144, 0);
        mbar_wait(bars + 8 * (A1_NST + 3), 1);
        TSTAMP1T(9, 256);
        const ulonglong2* hin = g_halo + ((size_t)(layer * 16 + mb - 1) * 8 + hg) * 640 + t;
        ulonglong2 hv[5];
        if (mb > 0) {
#pragma unroll 1
            for (int it = 0; it < SPIN_MAX; it++) {
                bool ok = true;
#pragma unroll
                for (int k = 0; k < 5; k++) hv[k] = ld_tag2(hin + 128 * k);
#pragma unroll
                for (int k = 0; k < 5; k++) ok = ok && tag_ok(hv[k], tag);
                if (ok) break;
            }
        } else {
#pragma unroll
            for (int k = 0; k < 5; k++) hv[k] = make_ulonglong2(0, 0);
        }
        TSTAMP1T(11, 256);
        unsigned char* hd = stg + A1_SM_KV + ((t & 31) >> 2) * A1_KVP + (t & 3) * 4 + (t >> 5) * 16;
#pragma unroll
        for (int k = 0; k < 5; k++) {
            *reinterpret_cast<uint32_t*>(hd + 64 * k) = (uint32_t)hv[k].x;
            *reinterpret_cast<uint32_t*>(hd + 64 * k + 8 * A1_KVP) = (uint32_t)hv[k].y;
        }
        __syncwarp();
        if ((tid & 31) == 0) mbar_arrive(bar_kv);
    } else {
        pdl_sync();
        SPAN(1 + 4 * layer, 1);
        TSTAMP1(0);
        if (threadIdx.x == 0) { GSTAMP(g_tim1, 15); }
        TSTAMP3(0);
        float acc[120];
#pragma unroll
        for (int i = 0; i < 120; i++) acc[i] = 0.f;
        if (layer == 0) a1_mainloop<0>(acc, sbase, bars, tile); else a1_mainloop<1>(acc, sbase, bars, tile);
        const int lane = tid & 31, warp = tid >> 5, g = lane >> 2, t = lane & 3;
        mbar_wait(bar_stat, 0);
        mbar_wait(bars + 8 * (A1_NST + 3), 1);
        const float2 sa_ = rst[16 * warp + g], sb_ = rst[16 * warp + g + 8];
        wgmma_wait<0>();
        TSTAMP1(2);
        uint32_t f[30][2];
        auto norm = [&](int j0) {
            float2 cc[10];
#pragma unroll
            for (int j = 0; j < 10; j++) cc[j] = *reinterpret_cast<const float2*>(cs + 8 * (j0 + j) + 2 * t);
#pragma unroll
            for (int j = 0; j < 10; j++) {
                const float* a = acc + 4 * (j0 + j);
                f[j0 + j][0] = pack2(fmaf(-sa_.x, cc[j].x, a[0]) * sa_.y, fmaf(-sa_.x, cc[j].y, a[1]) * sa_.y);
                f[j0 + j][1] = pack2(fmaf(-sb_.x, cc[j].x, a[2]) * sb_.y, fmaf(-sb_.x, cc[j].y, a[3]) * sb_.y);
            }
        };
        norm(10); norm(20);
        if (warp == 7) {
            ulonglong2* hout = g_halo + ((size_t)(layer * 16 + mb) * 8 + hg) * 640 + lane;
#pragma unroll
            for (int j = 0; j < 20; j++) st_tag2(hout + 32 * j, f[10 + j][0], f[10 + j][1], tag);
        }
        const uint32_t kvw = sbase + A1_SM_KV + 16 * warp * A1_KVP;
        const uint32_t mrow = kvw + (lane & 15) * A1_KVP + (lane >> 4) * 16;
#pragma unroll
        for (int j = 0; j < 20; j += 2) stsm_x4(mrow + 16 * A1_KVP + 16 * j, f[10 + j][0], f[10 + j][1], f[11 + j][0], f[11 + j][1]);
        __syncwarp();
        if (lane == 0) mbar_arrive(bar_kv + 8 * (warp + 1));
        norm(0);
        TSTAMP1T(10, 64);
        float sc[4][4][4];
        uint32_t qs[4][2];
#pragma unroll
        for (int h = 0; h < 4; h++) {
            const int jb = 5 * (h >> 1) + 3 * (h & 1), js = 5 * (h >> 1) + 2;
            qs[h][0] = (t >> 1) == (h & 1) ? f[js][0] : 0u; qs[h][1] = (t >> 1) == (h & 1) ? f[js][1] : 0u;
#pragma unroll
            for (int nt = 2; nt < 4; nt++) {
#pragma unroll
                for (int e = 0; e < 4; e++) sc[h][nt][e] = 0.f;
                mma_bf16(sc[h][nt], f[jb][0], f[jb][1], f[jb + 1][0], f[jb + 1][1], f[10 + jb][nt - 2], f[11 + jb][nt - 2]);
                mma_bf16_k8(sc[h][nt], qs[h][0], qs[h][1], f[10 + js][nt - 2]);
            }
        }
        mbar_wait(bar_kv + 8 * warp, 0);
        TSTAMP1(8);
        uint32_t kp[10][2];
#pragma unroll
        for (int j = 0; j < 10; j += 2) ldsm_x4(&kp[j][0], mrow + 16 * j);
#pragma unroll
        for (int h = 0; h < 4; h++) {
            const int jb = 5 * (h >> 1) + 3 * (h & 1), js = 5 * (h >> 1) + 2;
#pragma unroll
            for (int nt = 0; nt < 2; nt++) {
#pragma unroll
                for (int e = 0; e < 4; e++) sc[h][nt][e] = 0.f;
                mma_bf16(sc[h][nt], f[jb][0], f[jb][1], f[jb + 1][0], f[jb + 1][1], kp[jb][nt], kp[jb + 1][nt]);
                mma_bf16_k8(sc[h][nt], qs[h][0], qs[h][1], kp[js][nt]);
            }
        }
        uint32_t vb[10][4];
#pragma unroll
        for (int j = 0; j < 10; j++) ldsm_x4_t(vb[j], kvw + lane * A1_KVP + 160 + 16 * j);
        TSTAMP1T(3, 64);
        const bool odd = g & 1, hi = t > (g >> 1), edge = (mb | warp) == 0;
        float p[4][4], mx[4][2], sum[4][2];
#pragma unroll
        for (int h = 0; h < 4; h++) {
#pragma unroll
            for (int r = 0; r < 2; r++) {
                const float a = odd ? sc[h][1 + r][2 * r + 1] : sc[h][1 + r][2 * r];
                const float b0 = odd ? sc[h][r][2 * r + 1] : sc[h][r][2 * r], b1 = odd ? sc[h][2 + r][2 * r + 1] : sc[h][2 + r][2 * r];
                const uint32_t w = pack2(a, hi ? b0 : b1);
                const uint32_t w2 = pack2(__uint_as_float(w << 16) * 0.22360679774997896f, __uint_as_float(w & 0xffff0000u) * 0.22360679774997896f);
                p[h][2 * r] = __uint_as_float(w2 << 16); p[h][2 * r + 1] = __uint_as_float(w2 & 0xffff0000u);
            }
            if (edge) {
                p[h][0] = -1.0e9f;
                if (hi) { p[h][1] = -1.0e9f; p[h][3] = -1.0e9f; }
            }
            mx[h][0] = fmaxf(p[h][0], p[h][1]); mx[h][1] = fmaxf(p[h][2], p[h][3]);
        }
#pragma unroll
        for (int o = 1; o <= 2; o <<= 1)
#pragma unroll
            for (int h = 0; h < 4; h++)
#pragma unroll
                for (int r = 0; r < 2; r++) mx[h][r] = fmaxf(mx[h][r], __shfl_xor_sync(~0u, mx[h][r], o));
#pragma unroll
        for (int h = 0; h < 4; h++)
#pragma unroll
            for (int r = 0; r < 2; r++) {
                p[h][2 * r] = __expf(p[h][2 * r] - mx[h][r]); p[h][2 * r + 1] = __expf(p[h][2 * r + 1] - mx[h][r]);
                sum[h][r] = p[h][2 * r] + p[h][2 * r + 1];
            }
#pragma unroll
        for (int o = 1; o <= 2; o <<= 1)
#pragma unroll
            for (int h = 0; h < 4; h++)
#pragma unroll
                for (int r = 0; r < 2; r++) sum[h][r] += __shfl_xor_sync(~0u, sum[h][r], o);
        TSTAMP1T(5, 64);
        const uint32_t selA = odd ? 0x1044u : 0x4410u, selB = odd ? 0x3244u : 0x4432u, selH = hi ? selB : 0x4444u, selL = hi ? 0x4444u : selB;
        const uint32_t orow = sbase + A1_SM_O + (16 * warp + (lane & 15)) * 160 + (lane >> 4) * 16;
        uint32_t ob[10][2];
#pragma unroll
        for (int P = 0; P < 2; P++) {
            float os[2][4];
#pragma unroll
            for (int e = 0; e < 2; e++) {
                const int h = 2 * P + e;
                const float i0 = __fdividef(1.0f, sum[h][0]), i1 = __fdividef(1.0f, sum[h][1]);
                const uint32_t w0 = pack2(p[h][0] * i0, p[h][1] * i0), w1 = pack2(p[h][2] * i1, p[h][3] * i1);
                const uint32_t a00 = __byte_perm(w0, 0, selH), a02 = __byte_perm(w0, 0, selA), a03 = __byte_perm(w1, 0, selH);
                const uint32_t a10 = __byte_perm(w0, 0, selL), a11 = __byte_perm(w1, 0, selA), a13 = __byte_perm(w1, 0, selL);
#pragma unroll
                for (int dt = 0; dt < 3; dt++) {
                    const int j = 5 * P + (dt < 2 ? 3 * e + dt : 2);
                    float o[4] = {0.f, 0.f, 0.f, 0.f};
                    mma_bf16(o, a00, 0u, a02, a03, vb[j][0], vb[j][1]);
                    mma_bf16(o, a10, a11, 0u, a13, vb[j][2], vb[j][3]);
                    if (dt < 2) { ob[j][0] = pack2(o[0], o[1]); ob[j][1] = pack2(o[2], o[3]); }
                    else { os[e][0] = o[0]; os[e][1] = o[1]; os[e][2] = o[2]; os[e][3] = o[3]; }
                }
            }
            ob[5 * P + 2][0] = t < 2 ? pack2(os[0][0], os[0][1]) : pack2(os[1][0], os[1][1]);
            ob[5 * P + 2][1] = t < 2 ? pack2(os[0][2], os[0][3]) : pack2(os[1][2], os[1][3]);
        }
#pragma unroll
        for (int j = 0; j < 10; j += 2) stsm_x4(orow + 16 * j, ob[j][0], ob[j][1], ob[j + 1][0], ob[j + 1][1]);
        fence_async_smem();
        __syncwarp();
        if (lane == 0) tma_store_2d(&tmOst, hg * 80, mb * 128 + 16 * warp, sbase + A1_SM_O + 16 * warp * 160);
        TSTAMP1T(4, 64);
        TSTAMP1(1);
        GSTAMP(g_tim1, 14);
        SPAN(1 + 4 * layer, 3);
    }
}

constexpr int A2_THREADS = 288;
constexpr int A2_NA = 6;
constexpr int A2_WPRE = 4;
constexpr int A2_SM_A = 10 * WO_STAGE;
constexpr int A2_SM_R = A2_SM_A + A2_NA * 16384;
constexpr int A2_SM_BAR = A2_SM_R + 20480;
constexpr int A2_SMEM = A2_SM_BAR + 256 + 1024;

__global__ void __launch_bounds__(A2_THREADS, 1) a2_kernel(const int layer, const __grid_constant__ CUtensorMap tmO, const __grid_constant__ CUtensorMap tmR,
                                                           const __grid_constant__ CUtensorMap tmX1) {
    extern __shared__ unsigned char smraw[];
    const uint32_t sbase = (smem_u32(smraw) + 1023) & ~1023u;
    const uint32_t bars = sbase + A2_SM_BAR, bar_e = bars + 80, bar_r = bars + 128, bar_w = bars + 136;
    const int tid = threadIdx.x, wg = tid >> 7;
    SPAN(2 + 4 * layer, 0);
    const int tile = sm_tile(2 * layer + 1);
    if (tile >= 128) return;
    const int mb = tile >> 3, cg = tile & 7;
    if (tid == 256) {
        mbar_init(bar_w, 1);
        asm volatile("fence.mbarrier_init.release.cluster;" ::: "memory");
        mbar_expect_tx(bar_w, A2_WPRE * WO_STAGE);
        bulk_load(sbase, reinterpret_cast<const unsigned char*>(g_wo) + cg * 10 * WO_STAGE, A2_WPRE * WO_STAGE, bar_w);
        mbar_init(bar_w + 8, 1); mbar_init(bar_r, 1);
        mbar_expect_tx(bar_w + 8, (10 - A2_WPRE) * WO_STAGE);
        mbar_expect_tx(bar_r, 20480);
        asm volatile("fence.mbarrier_init.release.cluster;" ::: "memory");
    } else if ((tid & 31) == 0) {
        const int w = tid >> 5;
        mbar_init(bars + 16 * w, w < 5 ? 1 : 2);
        mbar_init(bars + 16 * w + 8, w < 5 ? 1 : 2);
        if (w < 5) { mbar_expect_tx(bars + 16 * w, 16384); mbar_expect_tx(bars + 16 * w + 8, 16384); }
        else prefetch_tmap(w == 5 ? &tmO : w == 6 ? &tmR : &tmX1);
        asm volatile("fence.mbarrier_init.release.cluster;" ::: "memory");
    }
    __syncthreads();
    pdl_sync();
    SPAN(2 + 4 * layer, 1);
    TSTAMP2(0);
    TSTAMP4(0);
    if (threadIdx.x == 0) { GSTAMP(g_tim2, 15); }
    if (wg == 2) {
        if (tid == 256) {
            for (int kb = 0; kb < 10; kb++) {
                if (kb >= A2_NA) mbar_wait(bar_e + 8 * (kb - A2_NA), 0);
                tma_load_2d(sbase + A2_SM_A + (kb % A2_NA) * 16384, &tmO, kb * 64, mb * 128, bars + 8 * kb);
                if (kb == 2) bulk_load(sbase + A2_WPRE * WO_STAGE, reinterpret_cast<const unsigned char*>(g_wo) + (cg * 10 + A2_WPRE) * WO_STAGE, (10 - A2_WPRE) * WO_STAGE, bar_w + 8);
                if (kb == A2_NA - 1) {
                    if (layer == 0) tma_load_2d(sbase + A2_SM_R, &tmR, cg * 80, mb * 128, bar_r);
                    else { tma_load_2d(sbase + A2_SM_R, &tmR, mb * 128, cg * 80, bar_r); tma_load_2d(sbase + A2_SM_R + 10240, &tmR, mb * 128 + 64, cg * 80, bar_r); }
                }
            }
        }
    } else {
        const int lane = tid & 31, warp = tid >> 5, g = lane >> 2, t = lane & 3;
        const int row = layer * SEQ + mb * 128 + 16 * warp + g;
        const unsigned short pv0 = __ldcg(reinterpret_cast<const unsigned short*>(g_piv) + row), pv1 = __ldcg(reinterpret_cast<const unsigned short*>(g_piv) + row + 8);
        float acc[40];
#pragma unroll
        for (int i = 0; i < 40; i++) acc[i] = 0.f;
        for (int kb = 0; kb < 10; kb++) {
            if (kb == 0) TSTAMP4(11);
            if (kb == 0 || kb == A2_WPRE) mbar_wait(kb ? bar_w + 8 : bar_w, 0);
            mbar_wait(bars + 8 * kb, 0);
            TSTAMP4(1 + kb);
            const uint32_t sa = sbase + A2_SM_A + (kb % A2_NA) * 16384 + wg * 8192, sb = sbase + kb * WO_STAGE;
            wgmma_fence();
#pragma unroll
            for (int kk = 0; kk < 4; kk++) wgmma_n80<0, 0>(acc, make_desc(sa + kk * 32, 16, 1024, 1), make_desc(sb + kk * 32, 16, 1024, 1));
            wgmma_commit();
            wgmma_wait<1>();
            if (kb > 0 && kb <= A2_NA && (tid & 127) == 0) mbar_arrive(bar_e + 8 * (kb - 1));
        }
        const uint32_t trow = ((lane & 7) + 8 * (lane >> 4)) * 128 + (((2 * (warp & 3) + ((lane >> 3) & 1)) ^ (lane & 7)) << 4);
        uint32_t xr[10][2];
        mbar_wait(bar_r, 0);
        if (layer == 0) {
#pragma unroll
            for (int j = 0; j < 10; j += 2) ldsm_x4(&xr[j][0], sbase + A2_SM_R + (16 * warp + (lane & 15)) * 160 + (lane >> 4) * 16 + 16 * j);
        } else {
#pragma unroll
            for (int j = 0; j < 10; j += 2) ldsm_x4_t(&xr[j][0], sbase + A2_SM_R + wg * 10240 + trow + 1024 * j);
        }
        mbar_wait(bar_e + 8 * (4 + wg), 0);
        wgmma_wait<0>();
        TSTAMP2(1);
        const float p0 = __uint_as_float((uint32_t)pv0 << 16), p1 = __uint_as_float((uint32_t)pv1 << 16);
        float s[4] = {0.f, 0.f, 0.f, 0.f};
#pragma unroll
        for (int j = 0; j < 10; j++) {
#pragma unroll
            for (int hh = 0; hh < 2; hh++) {
                const uint32_t a = pack2(acc[4 * j + 2 * hh], acc[4 * j + 2 * hh + 1]);
                const __nv_bfloat162 r = __hadd2_rn(*reinterpret_cast<const __nv_bfloat162*>(&xr[j][hh]), *reinterpret_cast<const __nv_bfloat162*>(&a));
                const uint32_t w = *reinterpret_cast<const uint32_t*>(&r);
                xr[j][hh] = w;
                const float d0 = __uint_as_float(w << 16) - (hh ? p1 : p0), d1 = __uint_as_float(w & 0xffff0000u) - (hh ? p1 : p0);
                s[2 * hh] += d0 + d1;
                s[2 * hh + 1] = fmaf(d0, d0, fmaf(d1, d1, s[2 * hh + 1]));
            }
        }
        const uint32_t so = sbase + A2_SM_A + (4 + wg) * 16384;
#pragma unroll
        for (int j = 0; j < 10; j += 2) stsm_x4_t(so + trow + 1024 * j, xr[j][0], xr[j][1], xr[j + 1][0], xr[j + 1][1]);
        fence_async_smem();
        TSTAMP2(2);
#pragma unroll
        for (int o = 1; o <= 2; o <<= 1)
#pragma unroll
            for (int i = 0; i < 4; i++) s[i] += __shfl_xor_sync(~0u, s[i], o);
        if (t < 2) asm volatile("red.relaxed.gpu.global.add.v2.f32 [%0], {%1, %2};" ::"l"(g_sum + layer * SEQ + (g >> 1) * 512 + (mb * 16 + 2 * warp + t) * 2 + (g & 1)), "f"(t ? s[2] : s[0]), "f"(t ? s[3] : s[1]) : "memory");
        if (wg) asm volatile("bar.sync 2, 128;" ::: "memory"); else asm volatile("bar.sync 1, 128;" ::: "memory");
        TSTAMP2(3);
        if ((tid & 127) == 0) tma_store_2d(&tmX1, mb * 128 + 64 * wg, cg * 80, so);
        TSTAMP2(4);
        GSTAMP(g_tim2, 14);
        SPAN(2 + 4 * layer, 3);
    }
}

static int h_nsm;
static CUtensorMap h_tmX0, h_tmX1, h_tmOst, h_tmO, h_tmR0, h_tmR1, h_tmX1st, h_tmOut;
typedef CUresult (*PFN_encodeTiled)(CUtensorMap*, CUtensorMapDataType, cuuint32_t, void*, const cuuint64_t*, const cuuint64_t*,
                                    const cuuint32_t*, const cuuint32_t*, CUtensorMapInterleave, CUtensorMapSwizzle,
                                    CUtensorMapL2promotion, CUtensorMapFloatOOBfill);
static void make_tmap(CUtensorMap* tm, const void* ptr, uint64_t cols, uint64_t rows, uint32_t bc, uint32_t br, CUtensorMapSwizzle sw, uint64_t pitch = 0) {
    static PFN_encodeTiled fn = nullptr;
    if (!fn) {
        void* p = nullptr; cudaDriverEntryPointQueryResult qr;
        cudaGetDriverEntryPoint("cuTensorMapEncodeTiled", &p, cudaEnableDefault, &qr);
        fn = (PFN_encodeTiled)p;
    }
    cuuint64_t dims[2] = {cols, rows}; cuuint64_t strides[1] = {(pitch ? pitch : cols) * 2};
    cuuint32_t box[2] = {bc, br}; cuuint32_t es[2] = {1, 1};
    fn(tm, CU_TENSOR_MAP_DATA_TYPE_BFLOAT16, 2, const_cast<void*>(ptr), dims, strides, box, es, CU_TENSOR_MAP_INTERLEAVE_NONE, sw,
       CU_TENSOR_MAP_L2_PROMOTION_L2_128B, CU_TENSOR_MAP_FLOAT_OOB_FILL_NONE);
}
template <typename... Args>
static void launch_pdl(void (*kern)(Args...), int grid, int block, int smem, Args... args) {
    cudaLaunchConfig_t cfg = {};
    cfg.gridDim = dim3(grid); cfg.blockDim = dim3(block); cfg.dynamicSmemBytes = smem; cfg.stream = cudaStreamPerThread;
    cudaLaunchAttribute at[1];
    at[0].id = cudaLaunchAttributeProgrammaticStreamSerialization; at[0].val.programmaticStreamSerializationAllowed = 1;
    cfg.attrs = at; cfg.numAttrs = 1;
    cudaLaunchKernelEx(&cfg, kern, args...);
}
static void launch_stage(int k, void* const* d_in, void* d_out) {
    const KgIn kg = {(const bf16*)d_in[4], (const bf16*)d_in[5], (const bf16*)d_in[6], (const bf16*)d_in[7], (const bf16*)d_in[8], (const bf16*)d_in[0], (const bf16*)d_in[1], (const bf16*)d_in[2]};
    switch (k) {
        case 0: kgen_kernel<<<DM, KG_THREADS, 0, cudaStreamPerThread>>>(kg); break;
        case 1: launch_pdl(a1_kernel, h_nsm, A1_THREADS, A1_SMEM, 0, (const bf16*)d_in[0], h_tmX0, h_tmR1, h_tmOst); break;
        case 2: launch_pdl(a2_kernel, h_nsm, A2_THREADS, A2_SMEM, 0, h_tmO, h_tmR0, h_tmX1st); break;
        case 3: launch_pdl(conv_kernel, DM / CV_CPB, CV_THREADS, CV_SMEM, (const bf16*)d_in[9], 0, h_tmOut); break;
        case 5: launch_pdl(a1_kernel, h_nsm, A1_THREADS, A1_SMEM, 1, (const bf16*)d_in[0], h_tmX1, h_tmR1, h_tmOst); break;
        case 6: launch_pdl(a2_kernel, h_nsm, A2_THREADS, A2_SMEM, 1, h_tmO, h_tmR1, h_tmX1st); break;
        case 7: launch_pdl(conv_kernel, DM / CV_CPB, CV_THREADS, CV_SMEM, (const bf16*)d_in[9], 1, h_tmOut); break;
        default: break;
    }
}
static int n_stage_kernels() { return 9; }
static const char* stage_name(int k) { const char* n[] = {"kgen", "a1", "a2", "conv", "tr", "a1", "a2", "conv", "tr"}; return n[k]; }

extern "C" void kernel_launch(void* const* d_in, const int* in_sizes, int n_in, void* d_out, int out_size) {
    (void)in_sizes; (void)n_in; (void)out_size;
    static const void *p_in = nullptr, *p_out = nullptr;
    if (p_in != d_in[0] || p_out != d_out) {
        cudaFuncSetAttribute(conv_kernel, cudaFuncAttributeMaxDynamicSharedMemorySize, CV_SMEM);
        cudaFuncSetAttribute(kgen_kernel, cudaFuncAttributePreferredSharedMemoryCarveout, 100);
        cudaFuncSetAttribute(a1_kernel, cudaFuncAttributeMaxDynamicSharedMemorySize, A1_SMEM);
        cudaFuncSetAttribute(a2_kernel, cudaFuncAttributeMaxDynamicSharedMemorySize, A2_SMEM);
        int dev; cudaGetDevice(&dev); cudaDeviceGetAttribute(&h_nsm, cudaDevAttrMultiProcessorCount, dev);
        if (h_nsm != 132) h_nsm = 128;
        void *po, *px1, *px2;
        cudaGetSymbolAddress(&po, g_o); cudaGetSymbolAddress(&px1, g_x1T); cudaGetSymbolAddress(&px2, g_xcT);
        make_tmap(&h_tmO, po, 640, 2048, 64, 128, CU_TENSOR_MAP_SWIZZLE_128B);
        make_tmap(&h_tmOst, po, 640, 2048, 80, 16, CU_TENSOR_MAP_SWIZZLE_NONE);
        make_tmap(&h_tmX0, d_in[0], 640, 2048, 64, 128, CU_TENSOR_MAP_SWIZZLE_128B);
        make_tmap(&h_tmX1, px2, 2048, 640, 64, 64, CU_TENSOR_MAP_SWIZZLE_128B, XCP);
        make_tmap(&h_tmR0, d_in[0], 640, 2048, 80, 128, CU_TENSOR_MAP_SWIZZLE_NONE);
        make_tmap(&h_tmR1, px2, 2048, 640, 64, 80, CU_TENSOR_MAP_SWIZZLE_128B, XCP);
        make_tmap(&h_tmX1st, px1, 2048, 640, 64, 80, CU_TENSOR_MAP_SWIZZLE_128B, XCP);
        make_tmap(&h_tmOut, d_out, 640, 2048, 80, 8, CU_TENSOR_MAP_SWIZZLE_NONE);
        p_in = d_in[0]; p_out = d_out;
    }
    for (int k = 0; k < n_stage_kernels(); k++) launch_stage(k, d_in, d_out);
}
```

```cpp
#include <cuda_runtime.h>
#include <cuda_bf16.h>
#include <stdint.h>
#include <cuda.h>

typedef __nv_bfloat16 bf16;

constexpr int SEQ = 2048;
constexpr int DM = 640;
constexpr int NMODE = 192;

__device__ __forceinline__ float bf2f(bf16 v) { return __bfloat162float(v); }
__device__ __forceinline__ float rbf(float v) {
    uint32_t r;
    asm("cvt.rn.bf16x2.f32 %0, %1, %2;" : "=r"(r) : "f"(v), "f"(0.f));
    return __uint_as_float(r);
}
__device__ __forceinline__ uint32_t pack2(float lo, float hi) {
    __nv_bfloat162 t = __floats2bfloat162_rn(lo, hi);
    return *reinterpret_cast<uint32_t*>(&t);
}
__device__ __forceinline__ void pdl_sync() {
    asm volatile("griddepcontrol.wait;" ::: "memory");
    asm volatile("griddepcontrol.launch_dependents;" ::: "memory");
}
__device__ __forceinline__ float sqrt_apx(float v) { float r; asm("sqrt.approx.ftz.f32 %0, %1;" : "=f"(r) : "f"(v)); return r; }
__device__ __forceinline__ float rcp_apx(float v) { float r; asm("rcp.approx.ftz.f32 %0, %1;" : "=f"(r) : "f"(v)); return r; }
__device__ __forceinline__ uint32_t smem_u32(const void* p) { return (uint32_t)__cvta_generic_to_shared(p); }

constexpr int TPAD = 16;
constexpr int DLEN = 544;
constexpr int TAP_W2 = DLEN * 8, TAP_W3 = TAP_W2 + 768, TAP_C = TAP_W3 + 768, TAPB = TAP_C + 384;
__device__ __align__(128) uint4 g_tap[DM * 128];
#define XPAD 64
constexpr int XCP = SEQ + XPAD;
__device__ __align__(128) bf16 g_x1T[DM * XCP];
__device__ __align__(128) bf16 g_xcT[DM * XCP];
__device__ __align__(128) bf16 g_o[SEQ * DM];
constexpr int WQ_STAGE = 240 * 128, WO_STAGE = 80 * 128;
__device__ __align__(128) uint4 g_wq[8 * 10 * WQ_STAGE / 16];
__device__ __align__(128) uint4 g_wo[8 * 10 * WO_STAGE / 16];
__device__ __align__(16) float g_csp[10 * 1920];
__device__ __align__(16) float2 g_sum[2 * SEQ];
__device__ __align__(16) bf16 g_piv[2 * SEQ];
__device__ __align__(128) bf16 g_yT[DM * XCP];
__device__ uint32_t g_epoch;
__device__ __align__(16) unsigned long long g_rstat[SEQ];
__device__ ulonglong2 g_part[16 * 8 * 128];
__device__ ulonglong2 g_halo[2 * 16 * 8 * 640];
__device__ __forceinline__ unsigned long long tagw(uint32_t payload, uint32_t tag) { return ((unsigned long long)tag << 32) | payload; }
__device__ __forceinline__ void st_tag2(ulonglong2* p, uint32_t a, uint32_t b, uint32_t tag) {
    asm volatile("st.global.cg.v2.u64 [%0], {%1, %2};" ::"l"(p), "l"(tagw(a, tag)), "l"(tagw(b, tag)) : "memory");
}
__device__ __forceinline__ ulonglong2 ld_tag2(const ulonglong2* p) {
    ulonglong2 v;
    asm volatile("ld.relaxed.gpu.global.v2.u64 {%0, %1}, [%2];" : "=l"(v.x), "=l"(v.y) : "l"(p) : "memory");
    return v;
}
__device__ __forceinline__ bool tag_ok(ulonglong2 v, uint32_t tag) { return (uint32_t)(v.x >> 32) == tag && (uint32_t)(v.y >> 32) == tag; }
__device__ __forceinline__ uint32_t ld_epoch() { uint32_t v; asm volatile("ld.relaxed.gpu.global.u32 %0, [%1];" : "=r"(v) : "l"(&g_epoch) : "memory"); return v + 1; }
constexpr int SPIN_MAX = 1 << 20;
__device__ uint32_t g_started[4];
__device__ __forceinline__ void sm_started(int slot) { asm volatile("red.relaxed.gpu.global.add.u32 [%0], 1;" ::"l"(g_started + slot) : "memory"); }
__device__ __noinline__ void sm_idle(int slot) {
    if (threadIdx.x) return;
    sm_started(slot);
    const uint32_t want = ld_epoch() * gridDim.x;
    pdl_sync();
#pragma unroll 1
    for (int it = 0; it < SPIN_MAX; it++) {
        uint32_t v;
        asm volatile("ld.relaxed.gpu.global.u32 %0, [%1];" : "=r"(v) : "l"(g_started + slot) : "memory");
        if ((int)(v - want) >= 0) break;
        __nanosleep(100);
    }
}
__device__ __forceinline__ int sm_tile() {
    uint32_t s;
    asm volatile("mov.u32 %0, %smid;" : "=r"(s));
    const uint32_t h = (s - 64) >> 1, q = (h * 37) >> 8;
    const int t0 = ((s >> 1) & 7) * 16 + (s >> 4) * 2 + (s & 1), t1 = (1 + h - 7 * q) * 16 + 8 + q * 2 + (s & 1), t2 = s - 124 < 8 ? s - 116 : 128;
    return gridDim.x == 128 ? (int)blockIdx.x : s < 64 ? t0 : s < 120 ? t1 : t2;
}
#define DBG_SYMS
#define TSTAMP(i)
#define TSTAMP1(i)
#define TSTAMP1T(i, t)
#define TSTAMP1X(i, t)
#define SPAN(k, i)
#define GSTAMP(arr, i)
#define TSTAMP2(i)
#define TSTAMP3(i)
#define TSTAMP4(i)
#define TSTAMPK(i, t)

__device__ __forceinline__ float2 cexp_at(float wr2, float wi, float p) {
    float er;
    asm("ex2.approx.ftz.f32 %0, %1;" : "=f"(er) : "f"(wr2 * p));
    float th = wi * p;
    const float k = rintf(th * 0.15915494309189535f);
    th = fmaf(k, -6.2831854820251465f, th);
    th = fmaf(k, 1.7484555314695172e-7f, th);
    return make_float2(er * __cosf(th), er * __sinf(th));
}
__device__ __forceinline__ float2 cmul(float2 a, float2 b) {
    return make_float2(fmaf(a.x, b.x, -a.y * b.y), fmaf(a.x, b.y, a.y * b.x));
}
__device__ __forceinline__ float2 csqr(float2 a) { return make_float2(fmaf(a.x, a.x, -a.y * a.y), (a.x + a.x) * a.y); }
__device__ __forceinline__ uint32_t packh(float2 v) {
    uint32_t r;
    asm("cvt.rn.f16x2.f32 %0, %1, %2;" : "=r"(r) : "f"(v.y), "f"(v.x));
    return r;
}
__device__ __forceinline__ void mma_f16(float* d, uint32_t a0, uint32_t a1, uint32_t a2, uint32_t a3, uint32_t b0, uint32_t b1) {
    asm volatile("mma.sync.aligned.m16n8k16.row.col.f32.f16.f16.f32 {%0,%1,%2,%3}, {%4,%5,%6,%7}, {%8,%9}, {%0,%1,%2,%3};"
                 : "+f"(d[0]), "+f"(d[1]), "+f"(d[2]), "+f"(d[3]) : "r"(a0), "r"(a1), "r"(a2), "r"(a3), "r"(b0), "r"(b1));
}

struct KgIn { const bf16 *logA, *Aim, *Cre, *Cim, *logdt, *x, *wqkv, *wo; };
constexpr int KG_THREADS = NMODE / 2;

__global__ void __launch_bounds__(KG_THREADS, 5) kgen_kernel(const KgIn in) {
    __shared__ __align__(128) uint4 tab[3 * 896];
    __shared__ __align__(16) unsigned short E[1024];
    const int d = blockIdx.x, tid = threadIdx.x, lane = tid & 31, warp = tid >> 5;
    SPAN(0, 0); SPAN(0, 1);
    TSTAMPK(0, 0);
    asm volatile("griddepcontrol.launch_dependents;" ::: "memory");
    const bf16 pdt = in.logdt[d];
    const uint32_t pla = reinterpret_cast<const uint32_t*>(in.logA)[d * KG_THREADS + tid], pai = reinterpret_cast<const uint32_t*>(in.Aim)[d * KG_THREADS + tid];
    const uint32_t pcr = reinterpret_cast<const uint32_t*>(in.Cre)[d * KG_THREADS + tid], pci = reinterpret_cast<const uint32_t*>(in.Cim)[d * KG_THREADS + tid];
    const bf16* pfq = tid < 30 ? in.wqkv + (size_t)(d * 30 + tid) * 64 : tid < 40 ? in.wo + (size_t)(d * 10 + tid - 30) * 64 : in.x + (size_t)(d * 32 + tid - 40) * 64;
    if (tid < 72) asm volatile("prefetch.global.L2 [%0];" ::"l"(pfq));
    reinterpret_cast<uint4*>(E)[tid] = make_uint4(0, 0, 0, 0);
    if (tid < 32) reinterpret_cast<uint4*>(E)[96 + tid] = make_uint4(0, 0, 0, 0);
    const uint32_t tw = smem_u32(tab) + warp * 14336;
    const int g = lane >> 2, t = lane & 3;
    const uint32_t sta = tw + lane * 128 + ((2 * (lane & 3) + ((lane >> 2) & 1)) << 4);
    const uint32_t lda = tw + t * 128 + ((g ^ (2 * t)) << 4);
    const uint32_t stb = tw + 12288 + lane * 64 + ((4 * ((lane >> 1) & 1) + ((lane >> 2) & 3)) << 3);
    const uint32_t ldb = tw + 12288 + t * 64 + ((g ^ (4 * (t >> 1))) << 3);
    auto sts4 = [&](int e, int off, uint32_t a, uint32_t b, uint32_t c, uint32_t dd) {
        asm volatile("st.shared.v4.u32 [%0], {%1,%2,%3,%4};" ::"r"((sta ^ (e << 4)) + off), "r"(a), "r"(b), "r"(c), "r"(dd) : "memory");
    };
    auto lds4 = [&](int sp, int off, uint32_t* r) {
        asm volatile("ld.shared.v4.u32 {%0,%1,%2,%3}, [%4];" : "=r"(r[0]), "=r"(r[1]), "=r"(r[2]), "=r"(r[3]) : "r"((lda ^ ((sp & 1) << 4)) + sp * 512 + off) : "memory");
    };
    const float dt = rbf(expf(bf2f(pdt)));
    float2 C[2], y1[2], z8[2], y128[2];
    float cmax = 0.f;
#pragma unroll
    for (int m = 0; m < 2; m++) {
        const float wr2 = -rbf(expf(__uint_as_float(m ? pla & 0xffff0000u : pla << 16))) * dt * 1.4426950408889634f;
        const float wi = __uint_as_float(m ? pai & 0xffff0000u : pai << 16) * dt;
        C[m] = make_float2(__uint_as_float(m ? pcr & 0xffff0000u : pcr << 16) * dt, -__uint_as_float(m ? pci & 0xffff0000u : pci << 16) * dt);
        cmax = fmaxf(cmax, fmaxf(fabsf(C[m].x), fabsf(C[m].y)));
        y1[m] = cexp_at(wr2, -wi, 1.f); z8[m] = cexp_at(wr2, wi, 8.f); y128[m] = cexp_at(wr2, -wi, 128.f);
    }
    const int ex = min(max((int)(__reduce_max_sync(~0u, __float_as_uint(cmax)) >> 23), 20), 240);
    const float scale = __uint_as_float((uint32_t)(127 + 10 + 127 - ex) << 23), unscale = 2.0f * __uint_as_float((uint32_t)(ex - 10) << 23);
    TSTAMPK(4, 0);
    float k2048 = 0.f;
    {
        float2 h0[2], h1[2], g0[2], g1[2], g2[2], g2b[2], g3[2], g4[2], y2[2], y4[2];
#pragma unroll
        for (int m = 0; m < 2; m++) {
            h0[m] = make_float2(1.f, 0.f); h1[m] = csqr(csqr(csqr(z8[m])));
            g0[m] = make_float2(C[m].x * scale, C[m].y * scale);
            g1[m] = cmul(g0[m], y128[m]);
            const float2 y256 = csqr(y128[m]), y512 = csqr(y256);
            g2b[m] = g2[m] = cmul(g0[m], y256); g3[m] = cmul(g0[m], y512); g4[m] = cmul(g3[m], y512);
            y2[m] = csqr(y1[m]); y4[m] = csqr(y2[m]);
        }
#pragma unroll
        for (int e = 0; e < 8; e++) {
            sts4(e, 0, packh(h0[0]), packh(h1[0]), packh(h0[1]), packh(h1[1]));
            sts4(e, 4096, packh(g0[0]), packh(g0[1]), packh(g1[0]), packh(g1[1]));
            sts4(e, 8192, packh(g2[0]), packh(g2[1]), packh((e & 1) ? cmul(g3[0], y4[0]) : g3[0]), packh((e & 1) ? cmul(g3[1], y4[1]) : g3[1]));
            asm volatile("st.shared.v2.u32 [%0], {%1,%2};" ::"r"(stb ^ (e << 3)), "r"(packh(g4[0])), "r"(packh(g4[1])) : "memory");
#pragma unroll
            for (int m = 0; m < 2; m++) {
                if (e < 7) {
                    h0[m] = e ? cmul(h0[m], z8[m]) : z8[m]; h1[m] = cmul(h1[m], z8[m]); g0[m] = cmul(g0[m], y1[m]); g1[m] = cmul(g1[m], y1[m]);
                    g2[m] = e == 3 ? cmul(g2b[m], y128[m]) : cmul(g2[m], y2[m]);
                    if (e & 1) g3[m] = cmul(g3[m], y128[m]);
                    g4[m] = cmul(g4[m], y128[m]);
                } else k2048 += fmaf(g4[m].x, y128[m].x, -g4[m].y * y128[m].y);
            }
        }
    }
    TSTAMPK(6, 0);
    const int job = warp * DM + d;
    const bool isq = job < 1200;
    uint32_t sw[16];
    unsigned char* sdst = nullptr;
    int sn = 0;
    if (job < 1600) {
        const int j2 = isq ? job : job - 1200, kb = j2 % 10, col = (j2 / 10) * 16 + (lane >> 3) * 4;
        if (isq) {
            const int sec = col / DM, r = col - sec * DM, hg = r / 80;
            sn = hg * 160 + sec * 80 + r;
            sdst = reinterpret_cast<unsigned char*>(g_wq) + (hg * 9 + kb) * WQ_STAGE;
        } else {
            sn = col;
            sdst = reinterpret_cast<unsigned char*>(g_wo) + ((col / 80) * 9 + kb) * WO_STAGE;
        }
        const int pitch = isq ? 3 * DM : DM;
        const bf16* src = (isq ? in.wqkv : in.wo) + (size_t)(kb * 64 + (lane & 7) * 8) * pitch + col;
#pragma unroll
        for (int i = 0; i < 8; i++) {
            const uint2 v = __ldg(reinterpret_cast<const uint2*>(src + i * pitch));
            sw[2 * i] = v.x; sw[2 * i + 1] = v.y;
        }
        sn += kb << 16;
    } else if (job < 1600 + 64) {
        reinterpret_cast<uint4*>(g_sum)[(job - 1600) * 32 + lane] = make_uint4(0, 0, 0, 0);
    }
    __syncwarp();
    float acc[5][4];
#pragma unroll
    for (int j = 0; j < 5; j++)
#pragma unroll
        for (int k = 0; k < 4; k++) acc[j][k] = 0.f;
#pragma unroll
    for (int sp = 0; sp < 8; sp++) {
        uint32_t a[4], b[4], c[4], e0, e1;
        lds4(sp, 0, a); lds4(sp, 4096, b); lds4(sp, 8192, c);
        asm volatile("ld.shared.v2.u32 {%0,%1}, [%2];" : "=r"(e0), "=r"(e1) : "r"((ldb ^ ((sp & 3) << 3)) + sp * 256) : "memory");
        mma_f16(acc[0], a[0], a[1], a[2], a[3], b[0], b[1]);
        mma_f16(acc[1], a[0], a[1], a[2], a[3], b[2], b[3]);
        mma_f16(acc[2], a[0], a[1], a[2], a[3], c[0], c[1]);
        mma_f16(acc[3], a[0], a[1], a[2], a[3], c[2], c[3]);
        mma_f16(acc[4], a[0], a[1], a[2], a[3], e0, e1);
    }
#pragma unroll
    for (int o = 16; o; o >>= 1) k2048 += __shfl_xor_sync(~0u, k2048, o);
    __syncwarp();
    {
        float* Pp = reinterpret_cast<float*>(tab + warp * 896);
#pragma unroll
        for (int h = 0; h < 2; h++) {
            const int b = g + 8 * h;
            *reinterpret_cast<float2*>(Pp + 8 * b + 2 * t) = make_float2(acc[0][2 * h] * unscale, acc[0][2 * h + 1] * unscale);
            *reinterpret_cast<float2*>(Pp + 128 + 8 * b + 2 * t) = make_float2(acc[1][2 * h] * unscale, acc[1][2 * h + 1] * unscale);
            *reinterpret_cast<float2*>(Pp + 256 + 4 * b + 2 * (t & 1) + 64 * (t >> 1)) = make_float2(acc[2][2 * h] * unscale, acc[2][2 * h + 1] * unscale);
            *reinterpret_cast<float2*>(Pp + 384 + 2 * b + 32 * t) = make_float2(acc[3][2 * h] * unscale, acc[3][2 * h + 1] * unscale);
            Pp[512 + b + 32 * t] = acc[4][2 * h] * unscale;
            Pp[512 + b + 32 * t + 16] = acc[4][2 * h + 1] * unscale;
        }
        if (lane == 0) Pp[640] = k2048 * unscale;
    }
    TSTAMPK(7, 0);
    __syncthreads();
    TSTAMPK(9, 0);
    const float* Kp = reinterpret_cast<const float*>(tab);
    auto ksum = [&](int i) -> float { return (Kp[i] + Kp[3584 + i]) + Kp[7168 + i]; };
    auto ksum4 = [&](int q) -> float4 {
        const float4 a = reinterpret_cast<const float4*>(Kp)[q], b = reinterpret_cast<const float4*>(Kp)[896 + q], c = reinterpret_cast<const float4*>(Kp)[1792 + q];
        return make_float4((a.x + b.x) + c.x, (a.y + b.y) + c.y, (a.z + b.z) + c.z, (a.w + b.w) + c.w);
    };
    uint32_t* E2w = reinterpret_cast<uint32_t*>(E);
    {
        float4 v = ksum4(tid);
        if (tid == 95) v.w -= rbf(ksum(384));
        const uint32_t lo = pack2(v.x, v.y), hi = pack2(v.z, v.w);
        if (tid < 64) { E2w[9 + 2 * tid] = lo; E2w[10 + 2 * tid] = hi; }
        else {
            const int l = 256 + 8 * (tid - 64);
            if (tid > 64) E[18 + l - 1] = (unsigned short)lo;
            E2w[9 + l / 2] = __byte_perm(lo, 0, 0x1010);
            E2w[10 + l / 2] = __byte_perm(lo, hi, 0x5432);
            E2w[11 + l / 2] = __byte_perm(hi, 0, 0x1010);
            E[18 + l + 6] = (unsigned short)(hi >> 16);
        }
    }
    if (tid < 64) {
        float4 v = ksum4(96 + tid);
        if (tid == 31) v.w -= rbf(ksum(512));
        const int o = (tid < 32 ? 317 : 417 - 64) + 2 * tid;
        E2w[o] = pack2(v.x, v.y); E2w[o + 1] = pack2(v.z, v.w);
    } else if (tid == 88) E[800 + 34 + 128] = (unsigned short)(__float_as_uint(rbf(ksum(640))) >> 16);
    if (job < 1600) {
        const int c = lane & 7, n = sn & 0xffff;
#pragma unroll
        for (int q = 0; q < 4; q++) {
            uint32_t w[4];
#pragma unroll
            for (int j = 0; j < 4; j++) w[j] = __byte_perm(sw[4 * j + (q >> 1)], sw[4 * j + 2 + (q >> 1)], (q & 1) ? 0x7632 : 0x5410);
            *reinterpret_cast<uint4*>(sdst + (n + q) * 128 + ((c ^ ((n + q) & 7)) << 4)) = make_uint4(w[0], w[1], w[2], w[3]);
        }
    }
    __syncthreads();
    g_tap[d * 128 + tid] = reinterpret_cast<const uint4*>(E)[tid];
    if (tid < 32) g_tap[d * 128 + 96 + tid] = reinterpret_cast<const uint4*>(E)[96 + tid];
    TSTAMPK(10, 0);
    if (isq) {
        float4 a = make_float4(0.f, 0.f, 0.f, 0.f);
#pragma unroll
        for (int i = 0; i < 8; i++) {
            a.x += __uint_as_float(sw[2 * i] << 16); a.y += __uint_as_float(sw[2 * i] & 0xffff0000u);
            a.z += __uint_as_float(sw[2 * i + 1] << 16); a.w += __uint_as_float(sw[2 * i + 1] & 0xffff0000u);
        }
#pragma unroll
        for (int o = 1; o <= 4; o <<= 1) {
            a.x += __shfl_xor_sync(~0u, a.x, o); a.y += __shfl_xor_sync(~0u, a.y, o);
            a.z += __shfl_xor_sync(~0u, a.z, o); a.w += __shfl_xor_sync(~0u, a.w, o);
        }
        if ((lane & 7) == 0) *reinterpret_cast<float4*>(g_csp + (sn >> 16) * 1920 + (sn & 0xffff)) = a;
    }
    TSTAMPK(11, 0);
    SPAN(0, 3);
}

#define CV_MODE 0
#define CV_SLEEP 100
constexpr int CV_CPB = 5;
constexpr int CV_THREADS = 512;
constexpr int UPADF = 128;
constexpr int ULEN = UPADF + SEQ + 80;
constexpr int XLEN = SEQ + 16;
constexpr int BX_5 = 0, BX_3 = 3264, BX_9 = 6528, BX_7 = 8960, BX_LEN = 11392;
constexpr int CV_SM_T = 0;
constexpr int CV_SM_B = CV_CPB * TAPB;
constexpr int CV_SM_U = CV_SM_B + CV_CPB * BX_LEN;
constexpr int CV_SM_X = CV_SM_U + CV_CPB * ULEN * 2;
constexpr int CV_SM_Y = CV_SM_X + CV_CPB * XLEN * 2;
constexpr int CV_SM_P = CV_SM_Y + CV_CPB * XLEN * 2;
constexpr int CV_SM_CNT = CV_SM_P + 6 * 4096;
constexpr int CV_SM_O = (CV_SM_CNT + 128 + 127) & ~127;
constexpr int CV_SMEM = CV_SM_O + 20480;
static_assert(CV_SM_B % 128 == 0 && CV_SM_CNT % 16 == 0, "layout");

__device__ __forceinline__ void mma_bf16(float* d, uint32_t a0, uint32_t a1, uint32_t a2, uint32_t a3, uint32_t b0, uint32_t b1) {
    asm volatile("mma.sync.aligned.m16n8k16.row.col.f32.bf16.bf16.f32 {%0,%1,%2,%3}, {%4,%5,%6,%7}, {%8,%9}, {%0,%1,%2,%3};"
                 : "+f"(d[0]), "+f"(d[1]), "+f"(d[2]), "+f"(d[3]) : "r"(a0), "r"(a1), "r"(a2), "r"(a3), "r"(b0), "r"(b1));
}
__device__ __forceinline__ void mma_bf16_k8(float* d, uint32_t a0, uint32_t a1, uint32_t b0) {
    asm volatile("mma.sync.aligned.m16n8k8.row.col.f32.bf16.bf16.f32 {%0,%1,%2,%3}, {%4,%5}, {%6}, {%0,%1,%2,%3};"
                 : "+f"(d[0]), "+f"(d[1]), "+f"(d[2]), "+f"(d[3]) : "r"(a0), "r"(a1), "r"(b0));
}
__device__ __forceinline__ void ldsm_x4(uint32_t* r, uint32_t addr) {
    asm volatile("ldmatrix.sync.aligned.m8n8.x4.shared.b16 {%0,%1,%2,%3}, [%4];"
                 : "=r"(r[0]), "=r"(r[1]), "=r"(r[2]), "=r"(r[3]) : "r"(addr));
}

__device__ __forceinline__ void ldsm_x4_t(uint32_t* r, uint32_t addr) {
    asm volatile("ldmatrix.sync.aligned.m8n8.x4.trans.shared.b16 {%0,%1,%2,%3}, [%4];"
                 : "=r"(r[0]), "=r"(r[1]), "=r"(r[2]), "=r"(r[3]) : "r"(addr));
}
__device__ __forceinline__ uint32_t ln2(uint32_t x, uint32_t m, float ra, float rb) {
    const __nv_bfloat162 d = __hsub2(*reinterpret_cast<const __nv_bfloat162*>(&x), *reinterpret_cast<const __nv_bfloat162*>(&m));
    const uint32_t w = *reinterpret_cast<const uint32_t*>(&d);
    return pack2(__uint_as_float(w << 16) * ra, __uint_as_float(w & 0xffff0000u) * rb);
}
__device__ __forceinline__ void cp_async16(uint32_t dst, const void* src) {
    asm volatile("cp.async.cg.shared.global [%0], [%1], 16;" ::"r"(dst), "l"(src));
}
__device__ __forceinline__ void cp_async_wait_all() { asm volatile("cp.async.wait_all;" ::: "memory"); }

template <bool FULL>
__device__ __forceinline__ void direct_pass(float (&acc)[8][4], uint32_t ub, uint32_t o0, uint32_t o1, const uint2* __restrict__ Tp, bool first_half) {
    uint32_t sw[8][8];
#pragma unroll
    for (int j = 0; j < 8; j++) { ldsm_x4(&sw[j][0], ub + o0 + j * 256); ldsm_x4(&sw[j][4], ub + o1 + j * 256); }
#pragma unroll
    for (int M = 0; M < 4; M++) {
#pragma unroll
        for (int i = 0; i < 4; i++) {
            const uint2 hi = Tp[128 * M + 16 * i], lo = Tp[128 * M + 16 * i - 8];
#pragma unroll
            for (int j = FULL ? 0 : M; j < 8; j++) mma_bf16(acc[j], hi.x, hi.y, lo.x, lo.y, sw[(j - M) & 7][2 * i], sw[(j - M) & 7][2 * i + 1]);
        }
        if (FULL) {
            ldsm_x4(&sw[7 - M][0], ub + o0 - (M + 1) * 256);
            if (M < 3) ldsm_x4(&sw[7 - M][4], ub + o1 - (M + 1) * 256);
        }
    }
    if (first_half) {
        const uint2 hi = Tp[512], lo = Tp[504];
#pragma unroll
        for (int j = FULL ? 0 : 4; j < 8; j++) mma_bf16(acc[j], hi.x, hi.y, lo.x, lo.y, sw[(j - 4) & 7][0], sw[(j - 4) & 7][1]);
    }
}
__device__ __forceinline__ void mbar_init(uint32_t bar, int count) { asm volatile("mbarrier.init.shared::cta.b64 [%0], %1;" ::"r"(bar), "r"(count)); }
__device__ __forceinline__ void mbar_arrive(uint32_t bar) { asm volatile("mbarrier.arrive.shared::cta.b64 _, [%0];" ::"r"(bar) : "memory"); }
__device__ __forceinline__ void mbar_wait(uint32_t bar, uint32_t parity) {
    asm volatile("{\n.reg .pred p;\nWAIT_LOOP:\n"
                 "mbarrier.try_wait.parity.shared::cta.b64 p, [%0], %1;\n"
                 "@p bra.uni WAIT_DONE;\nbra.uni WAIT_LOOP;\nWAIT_DONE:\n}" ::"r"(bar), "r"(parity) : "memory");
}

__device__ __forceinline__ void mbar_expect_tx(uint32_t bar, uint32_t bytes) {
    asm volatile("mbarrier.arrive.expect_tx.shared::cta.b64 _, [%0], %1;" ::"r"(bar), "r"(bytes) : "memory");
}
__device__ __forceinline__ void tma_load_2d(uint32_t dst, const void* tmap, int c0, int c1, uint32_t bar) {
    asm volatile("cp.async.bulk.tensor.2d.shared::cluster.global.mbarrier::complete_tx::bytes [%0], [%1, {%3, %4}], [%2];"
                 ::"r"(dst), "l"(tmap), "r"(bar), "r"(c0), "r"(c1) : "memory");
}
__device__ __forceinline__ void fence_async_smem() { asm volatile("fence.proxy.async.shared::cta;" ::: "memory"); }
__device__ __forceinline__ void bulk_load(uint32_t dst, const void* src, uint32_t bytes, uint32_t bar) {
    asm volatile("cp.async.bulk.shared::cluster.global.mbarrier::complete_tx::bytes [%0], [%1], %2, [%3];"
                 ::"r"(dst), "l"(src), "r"(bytes), "r"(bar) : "memory");
}
__device__ __forceinline__ void tma_store_2d(const void* tmap, int c0, int c1, uint32_t src) {
    asm volatile("cp.async.bulk.tensor.2d.global.shared::cta.bulk_group [%0, {%1, %2}], [%3];" ::"l"(tmap), "r"(c0), "r"(c1), "r"(src) : "memory");
    asm volatile("cp.async.bulk.commit_group;" ::: "memory");
    asm volatile("cp.async.bulk.wait_group.read 0;" ::: "memory");
}
__device__ __forceinline__ void stsm_x4(uint32_t addr, uint32_t r0, uint32_t r1, uint32_t r2, uint32_t r3) {
    asm volatile("stmatrix.sync.aligned.m8n8.x4.shared.b16 [%0], {%1,%2,%3,%4};" ::"r"(addr), "r"(r0), "r"(r1), "r"(r2), "r"(r3) : "memory");
}
__device__ __forceinline__ void stsm_x4_t(uint32_t addr, uint32_t r0, uint32_t r1, uint32_t r2, uint32_t r3) {
    asm volatile("stmatrix.sync.aligned.m8n8.x4.trans.shared.b16 [%0], {%1,%2,%3,%4};" ::"r"(addr), "r"(r0), "r"(r1), "r"(r2), "r"(r3) : "memory");
}
__device__ __forceinline__ void prefetch_tmap(const void* tmap) { asm volatile("prefetch.tensormap [%0];" ::"l"(tmap) : "memory"); }

__device__ __forceinline__ uint32_t fin2(uint32_t x, uint32_t y, uint32_t u, uint32_t dk) {
    typedef __nv_bfloat162 b2;
    const b2 r = __hadd2_rn(*reinterpret_cast<const b2*>(&x), __hadd2_rn(*reinterpret_cast<const b2*>(&y),
                            __hmul2_rn(*reinterpret_cast<const b2*>(&u), *reinterpret_cast<const b2*>(&dk))));
    return *reinterpret_cast<const uint32_t*>(&r);
}
__global__ void __launch_bounds__(CV_THREADS, 1) conv_kernel(const bf16* __restrict__ Dskip, int layer, const __grid_constant__ CUtensorMap tmOut) {
    extern __shared__ __align__(128) unsigned char sm[];
    SPAN(3 + 4 * layer, 0);
    bf16* Us = reinterpret_cast<bf16*>(sm + CV_SM_U);
    bf16* Xs = reinterpret_cast<bf16*>(sm + CV_SM_X);
    bf16* Ys = reinterpret_cast<bf16*>(sm + CV_SM_Y);
    const int tid = threadIdx.x, lane = tid & 31, warp = __shfl_sync(~0u, tid >> 5, 0);
    const int d0 = blockIdx.x * CV_CPB, tile = blockIdx.x; (void)tile;
    TSTAMP1X(9, 256);
    unsigned short dskr;
    asm volatile("ld.global.nc.u16 %0, [%1];" : "=h"(dskr) : "l"(Dskip + d0 + min(lane, CV_CPB - 1)));
    if (tid >= 256) {
        const int t2 = tid - 256;
        if (t2 == 0) {
            mbar_init(smem_u32(sm + CV_SM_CNT) + 104, 1);
            asm volatile("fence.mbarrier_init.release.cluster;" ::: "memory");
            mbar_expect_tx(smem_u32(sm + CV_SM_CNT) + 104, CV_CPB * 2048);
            bulk_load(smem_u32(sm + CV_SM_O), g_tap + d0 * 128, CV_CPB * 2048, smem_u32(sm + CV_SM_CNT) + 104);
        } else if (lane == 0) {
            mbar_init(smem_u32(sm + CV_SM_CNT) + 16 * (warp - 9), warp == 15 ? 16 : 1);
            if (warp < 15) mbar_init(smem_u32(sm + CV_SM_CNT) + 16 * (warp - 9) + 8, 1);
            else if (layer) prefetch_tmap(&tmOut);
        }
        if (t2 < 149) {
            const int k = t2;
            const int off = k < 18 ? BX_5 + 8 * k : k < 37 ? BX_3 + 8 * (k - 18) : k < 69 ? BX_9 + 8 * (k - 37) : k < 101 ? BX_7 + 8 * (k - 69)
                          : k < 133 ? 8 * (k - 101) : (UPADF + SEQ) * 2 + 8 * (k - 133);
#pragma unroll
            for (int c = 0; c < CV_CPB; c++) *reinterpret_cast<uint2*>(sm + (k < 101 ? CV_SM_B + c * BX_LEN : CV_SM_U + c * ULEN * 2) + off) = make_uint2(0, 0);
        }
        asm volatile("bar.sync 1, 256;" ::: "memory");
        TSTAMP1X(10, 256);
        mbar_wait(smem_u32(sm + CV_SM_CNT) + 104, 0);
        TSTAMP1X(11, 256);
#pragma unroll 1
        for (int r = t2; r < 392; r += 256) {
            const bool dd = r < 272, cc = r >= 368;
            const uint32_t* E2 = reinterpret_cast<const uint32_t*>(sm + CV_SM_O) + (dd ? r : r < 320 ? 300 + 2 * (r - 272) : cc ? 416 : 400 + 2 * (r - 320));
            const uint32_t* E3 = E2 + (dd ? 4 : cc ? 0 : 1);
            const uint32_t s0 = !cc ? 0x7610u : r == 382 ? 0x1044u : 0x4444u, s1 = !cc ? 0x7610u : r == 378 ? 0x1044u : 0x4444u;
            const uint32_t s2 = !cc ? 0x1032u : r == 381 ? 0x4410u : 0x4444u, s3 = !cc ? 0x1032u : r == 377 ? 0x4410u : 0x4444u;
            uint32_t w[CV_CPB][4];
#pragma unroll
            for (int c = 0; c < CV_CPB; c++) { w[c][0] = E2[512 * c]; w[c][1] = E2[512 * c + 1]; w[c][2] = E3[512 * c]; w[c][3] = E3[512 * c + 1]; }
#pragma unroll
            for (int c = 0; c < CV_CPB; c++) {
                const uint32_t a = __byte_perm(w[c][3], w[c][2], s1), b = __byte_perm(w[c][1], w[c][0], s2);
                *reinterpret_cast<uint4*>(sm + CV_SM_T + c * TAPB + r * 16) =
                    make_uint4(__byte_perm(w[c][1], w[c][0], s0), dd || cc ? a : b, dd || cc ? b : a, __byte_perm(w[c][3], w[c][2], s3));
            }
        }
        TSTAMP1X(12, 256);
        if (layer == 0) {
#pragma unroll
            for (int c = 0; c < CV_CPB; c++) reinterpret_cast<uint4*>(g_yT + (size_t)(d0 + c) * XCP)[t2] = make_uint4(~0u, ~0u, ~0u, ~0u);
        }
        pdl_sync();
        if (layer && blockIdx.x == 0 && t2 == 0) g_epoch = ld_epoch();
    } else {
        const uint4* ppv = reinterpret_cast<const uint4*>(g_piv + layer * SEQ) + tid;
        const float4* psv = reinterpret_cast<const float4*>(g_sum + layer * SEQ) + tid;
        const uint4* pxv = reinterpret_cast<const uint4*>(g_x1T + (size_t)d0 * XCP) + tid;
        asm volatile("" : "+l"(ppv), "+l"(psv), "+l"(pxv));
        pdl_sync();
        SPAN(3 + 4 * layer, 1);
        TSTAMP(0);
        if (threadIdx.x == 0) { GSTAMP(g_tim, 15); }
        float4 sv[4];
#pragma unroll
        for (int k = 0; k < 4; k++) sv[k] = __ldcg(psv + 256 * k);
        const uint4 pv = __ldcg(ppv);
        uint4 xv[CV_CPB];
#pragma unroll
        for (int c = 0; c < CV_CPB; c++) xv[c] = __ldcg(pxv + c * (XCP / 8));
        uint32_t mw[4];
        float rs[8];
#pragma unroll
        for (int k = 0; k < 4; k++) {
            const uint32_t pw = k == 0 ? pv.x : k == 1 ? pv.y : k == 2 ? pv.z : pv.w;
            const float d0_ = sv[k].x * (1.0f / DM), d1_ = sv[k].z * (1.0f / DM);
            mw[k] = pack2(__uint_as_float(pw << 16) + d0_, __uint_as_float(pw & 0xffff0000u) + d1_);
            const uint32_t vr = pack2(fmaxf(fmaf(-d0_, d0_, sv[k].y * (1.0f / DM)), 0.f), fmaxf(fmaf(-d1_, d1_, sv[k].w * (1.0f / DM)), 0.f));
            const uint32_t ve = pack2(__uint_as_float(vr << 16) + 1e-5f, __uint_as_float(vr & 0xffff0000u) + 1e-5f);
            const uint32_t sd = pack2(sqrt_apx(__uint_as_float(ve << 16)), sqrt_apx(__uint_as_float(ve & 0xffff0000u)));
            rs[2 * k] = rcp_apx(__uint_as_float(sd << 16)); rs[2 * k + 1] = rcp_apx(__uint_as_float(sd & 0xffff0000u));
        }
        if (rs[0] != 123.f) TSTAMP(13);
        const int ch = tid + UPADF / 8, pch = ch ^ ((ch >> 3) & 1);
#pragma unroll
        for (int c = 0; c < CV_CPB; c++) {
            *reinterpret_cast<uint4*>(Xs + c * XLEN + tid * 8) = xv[c];
            *reinterpret_cast<uint4*>(Us + c * ULEN + pch * 8) =
                make_uint4(ln2(xv[c].x, mw[0], rs[0], rs[1]), ln2(xv[c].y, mw[1], rs[2], rs[3]), ln2(xv[c].z, mw[2], rs[4], rs[5]), ln2(xv[c].w, mw[3], rs[6], rs[7]));
        }
    }
    __syncthreads();
    TSTAMP(1);
    const uint32_t rstart = warp < 8 ? (warp < 4 ? 0x02000000u : 0x06040000u) : (warp < 12 ? 0x0C0B0A08u : 0x1E1D150Fu);
    const uint32_t rcount = warp < 8 ? 0x02020000u : (warp < 12 ? 0x03010102u : 0x01010806u);
#pragma unroll 1
    for (int rd = (rstart >> (8 * (warp & 3))) & 0xff, re = rd + ((rcount >> (8 * (warp & 3))) & 0xff); rd < re; rd++) {
        const int i = 32 * rd + lane;
        if (i < CV_CPB * 193) {
            const int c = i / 193, chunk = i - c * 193 - 1, ch = chunk + UPADF / 8;
            const bf16* uc = Us + c * ULEN;
            const uint4 o = *reinterpret_cast<const uint4*>(uc + (ch ^ ((ch >> 3) & 1)) * 8);
            const uint2 lo = *reinterpret_cast<const uint2*>(uc + ((ch - 1) ^ (((ch - 1) >> 3) & 1)) * 8 + 4);
            const uint2 hi = *reinterpret_cast<const uint2*>(uc + ((ch + 1) ^ (((ch + 1) >> 3) & 1)) * 8);
            const uint32_t w[8] = {lo.x, lo.y, o.x, o.y, o.z, o.w, hi.x, hi.y};
            float v[16], b[8];
#pragma unroll
            for (int k = 0; k < 8; k++) { v[2 * k] = __uint_as_float(w[k] << 16); v[2 * k + 1] = __uint_as_float(w[k] & 0xffff0000u); }
            unsigned char* bx = sm + CV_SM_B + c * BX_LEN + chunk * 16;
#pragma unroll
            for (int k = 0; k < 8; k++) b[k] = v[k + 4] + (v[k + 3] + v[k + 5]);
            *reinterpret_cast<uint2*>(bx + BX_3 + 168) = make_uint2(pack2(b[0], b[1]), pack2(b[2], b[3]));
            *reinterpret_cast<uint2*>(bx + BX_3 + 176) = make_uint2(pack2(b[4], b[5]), pack2(b[6], b[7]));
#pragma unroll
            for (int k = 0; k < 8; k++) b[k] += v[k + 2] + v[k + 6];
            *reinterpret_cast<uint4*>(bx + BX_5 + 160) = make_uint4(pack2(b[0], b[1]), pack2(b[2], b[3]), pack2(b[4], b[5]), pack2(b[6], b[7]));
            if (chunk < 128) {
#pragma unroll
                for (int k = 0; k < 8; k++) b[k] += v[k + 1] + v[k + 7];
                *reinterpret_cast<uint4*>(bx + BX_7 + 272) = make_uint4(pack2(b[0], b[1]), pack2(b[2], b[3]), pack2(b[4], b[5]), pack2(b[6], b[7]));
#pragma unroll
                for (int k = 0; k < 8; k++) b[k] += v[k] + v[k + 8];
                *reinterpret_cast<uint4*>(bx + BX_9 + 272) = make_uint4(pack2(b[0], b[1]), pack2(b[2], b[3]), pack2(b[4], b[5]), pack2(b[6], b[7]));
            }
        }
    }
    __syncwarp();
    if (lane == 0) mbar_arrive(smem_u32(sm + CV_SM_CNT) + 96);
    TSTAMP(2);
    {
        const int g = lane >> 2, ti = lane & 3;
        const int e = g - 2 * ti;
        uint32_t lds_off[4];
        uint32_t off2, off3, offc;
        {
            const int mat = lane >> 3, r = lane & 7;
#pragma unroll
            for (int pr = 0; pr < 4; pr++) {
                const int iw = 2 * pr + (mat >> 1), half = mat & 1;
                const int chunk = (UPADF - 16 * iw + 16 * r + 8 * half) >> 3;
                lds_off[pr] = (uint32_t)((chunk ^ ((chunk >> 3) & 1)) * 16);
            }
            const int j2 = 13 + r + 8 * (mat >> 1), j3 = j2 + 2, i0 = 8 * (mat & 1);
            off2 = (j2 & 1) ? BX_3 + (4 * j2 + i0 + 84) * 2 : BX_5 + (4 * j2 + i0 + 80) * 2;
            off3 = ((j3 & 1) ? BX_7 : BX_9) + (8 * j3 + i0 + 136) * 2;
            const int cc = (UPADF + 16 * (r + (mat >> 1)) + i0) >> 3;
            offc = (uint32_t)((cc ^ ((cc >> 3) & 1)) * 16);
        }
        const uint32_t rtab = warp < 8 ? (warp < 4 ? 0x0B090200u : 0x0C0A0301u) : (warp < 12 ? 0x13111008u : 0x1412241Cu);
        const int rl = (rtab >> (8 * (warp & 3))) & 0xff, type = rl >> 3, c = rl & 7;
        const int H = (type == 1 || type == 2) ? 1 : 0, T0 = 8 * H;
        const uint2* Tc = reinterpret_cast<const uint2*>(sm + CV_SM_T + c * TAPB) + TPAD + e;
        const uint32_t ubase = smem_u32(Us + c * ULEN);
        const uint32_t bbase = smem_u32(sm + CV_SM_B + c * BX_LEN);
        float acc[8][4];
#pragma unroll
        for (int j = 0; j < 8; j++)
#pragma unroll
            for (int k = 0; k < 4; k++) acc[j][k] = 0.f;
#pragma unroll 1
        for (int pass = (type == 2 || type == 4) ? 1 : 0; pass < ((type == 1 || type == 3) ? 1 : 2); pass++) {
            const uint32_t o0 = pass ? lds_off[2] : lds_off[0], o1 = pass ? lds_off[3] : lds_off[1];
            if (H) direct_pass<true>(acc, ubase + T0 * 256, o0, o1, Tc + 64 * pass, pass == 0);
            else direct_pass<false>(acc, ubase, o0, o1, Tc + 64 * pass, pass == 0);
        }
        TSTAMP(6);
        mbar_wait(smem_u32(sm + CV_SM_CNT) + 96, 0);
        if (type != 1 && type != 4) {
            const uint32_t* w2 = reinterpret_cast<const uint32_t*>(sm + CV_SM_T + c * TAPB + TAP_W2) + (115 - 96) + 4 * g - 2 * ti;
            uint32_t f[10][2];
#pragma unroll
            for (int k = 0; k < 10; k++) { f[k][0] = w2[16 * k]; f[k][1] = w2[16 * k - 8]; }
            const uint32_t ab = bbase + off2 + (2 * T0 + 6) * 128;
            const int kmax = H ? 23 : 8;
            uint32_t a[3][4];
            ldsm_x4_t(a[0], ab);
            ldsm_x4_t(a[1], ab - 128);
#pragma unroll
            for (int kp = 0; kp < 24; kp++) {
                if (kp > kmax) break;
                if (kp < 22) ldsm_x4_t(a[(kp + 2) % 3], ab - min(kp + 2, kmax) * 128);
#pragma unroll
                for (int j = 0; j < 8; j++) {
                    const int ee = 2 * j - 14 + kp;
                    if (ee >= 0 && ee <= 9) mma_bf16(acc[j], a[kp % 3][0], a[kp % 3][1], a[kp % 3][2], a[kp % 3][3], f[ee][0], f[ee][1]);
                }
            }
        }
        TSTAMP(7);
        if (type != 2 && type != 4) {
            const uint32_t* w3 = reinterpret_cast<const uint32_t*>(sm + CV_SM_T + c * TAPB + TAP_W3) + (129 - 96) + 2 * (g - ti);
            uint32_t f[9][2];
#pragma unroll
            for (int k = 0; k < 9; k++) { f[k][0] = w3[16 * k]; f[k][1] = w3[16 * k - 8]; }
            const uint32_t ab = bbase + off3 + (T0 - 2) * 256;
            uint32_t a[3][4];
            ldsm_x4_t(a[0], ab);
            ldsm_x4_t(a[1], ab - H * 256);
#pragma unroll
            for (int kp = 0; kp < 9; kp++) {
                if (kp > T0) break;
                if (kp < 7) ldsm_x4_t(a[(kp + 2) % 3], ab - min(kp + 2, T0) * 256);
#pragma unroll
                for (int j = 0; j < 8; j++) {
                    const int dl = j - 7 + kp;
                    if (dl >= 0 && dl <= 8) mma_bf16(acc[j], a[kp % 3][0], a[kp % 3][1], a[kp % 3][2], a[kp % 3][3], f[dl][0], f[dl][1]);
                }
            }
            const uint2* Dc = reinterpret_cast<const uint2*>(sm + CV_SM_T + c * TAPB + TAP_C) + e;
            const uint2 h63 = Dc[16], h64 = Dc[32], l63 = Dc[8], l64 = Dc[24];
#pragma unroll
            for (int j = 0; j < 8; j++)
                if (j == 7 || H) {
                    uint32_t bq[4];
                    ldsm_x4(bq, ubase + offc + (T0 + j - 8) * 256);
                    mma_bf16(acc[j], h64.x, h64.y, l64.x, l64.y, bq[0], bq[1]);
                    mma_bf16(acc[j], h63.x, h63.y, l63.x, l63.y, bq[2], bq[3]);
                }
        }
        TSTAMP(8);
        const bool hi_half = (type == 2 || type == 4);
        if (type != 0) {
            const int pair = H ? c : 5;
            float4* give = reinterpret_cast<float4*>(sm + CV_SM_P + pair * 4096 + (hi_half ? 2048 : 0)) + lane;
            const float4* take = reinterpret_cast<const float4*>(sm + CV_SM_P + pair * 4096 + (hi_half ? 0 : 2048)) + lane;
            const uint32_t pb = smem_u32(sm + CV_SM_CNT) + pair * 16;
#pragma unroll
            for (int j = 0; j < 4; j++)
                give[32 * j] = hi_half ? make_float4(acc[j][0], acc[j][1], acc[j][2], acc[j][3]) : make_float4(acc[j + 4][0], acc[j + 4][1], acc[j + 4][2], acc[j + 4][3]);
            __syncwarp();
            if (lane == 0) mbar_arrive(pb + (hi_half ? 8 : 0));
            mbar_wait(pb + (hi_half ? 0 : 8), 0);
#pragma unroll
            for (int j = 0; j < 4; j++) {
                const float4 v = take[32 * j];
                acc[j][0] = (hi_half ? acc[j + 4][0] : acc[j][0]) + v.x; acc[j][1] = (hi_half ? acc[j + 4][1] : acc[j][1]) + v.y;
                acc[j][2] = (hi_half ? acc[j + 4][2] : acc[j][2]) + v.z; acc[j][3] = (hi_half ? acc[j + 4][3] : acc[j][3]) + v.w;
            }
        }
        const uint32_t dk = __shfl_sync(~0u, (uint32_t)dskr, c) * 0x10001u;
#pragma unroll 1
        for (int rnd = 0; rnd < (type == 0 ? 2 : 1); rnd++) {
            const int Q = 2 * H + (hi_half ? 1 : rnd);
            if (rnd) {
#pragma unroll
                for (int j = 0; j < 4; j++)
#pragma unroll
                    for (int k = 0; k < 4; k++) acc[j][k] = acc[j + 4][k];
            }
            const uint32_t ya = smem_u32(Ys + c * XLEN) + (128 * (4 * Q + (lane >> 4)) + 16 * (lane & 7) + 8 * ((lane >> 3) & 1)) * 2;
#pragma unroll
            for (int j = 0; j < 4; j += 2)
                asm volatile("stmatrix.sync.aligned.m8n8.x4.trans.shared.b16 [%0], {%1,%2,%3,%4};" ::"r"(ya + j * 256),
                             "r"(pack2(acc[j][0], acc[j][1])), "r"(pack2(acc[j][2], acc[j][3])),
                             "r"(pack2(acc[j + 1][0], acc[j + 1][1])), "r"(pack2(acc[j + 1][2], acc[j + 1][3])) : "memory");
            __syncwarp();
            uint4 yv[2], xv[2], uv[2];
#pragma unroll
            for (int k = 0; k < 2; k++) {
                const int t = 512 * Q + 256 * k + 8 * lane, cu = (t + UPADF) >> 3;
                yv[k] = *reinterpret_cast<const uint4*>(Ys + c * XLEN + t);
                xv[k] = *reinterpret_cast<const uint4*>(Xs + c * XLEN + t);
                uv[k] = *reinterpret_cast<const uint4*>(Us + c * ULEN + (cu ^ ((cu >> 3) & 1)) * 8);
            }
#pragma unroll
            for (int k = 0; k < 2; k++)
                asm volatile("st.relaxed.gpu.global.v4.u32 [%0], {%1,%2,%3,%4};" ::"l"((layer ? g_yT : g_xcT) + (size_t)(d0 + c) * XCP + 512 * Q + 256 * k + 8 * lane),
                             "r"(fin2(xv[k].x, yv[k].x, uv[k].x, dk)), "r"(fin2(xv[k].y, yv[k].y, uv[k].y, dk)), "r"(fin2(xv[k].z, yv[k].z, uv[k].z, dk)), "r"(fin2(xv[k].w, yv[k].w, uv[k].w, dk)) : "memory");
        }
        TSTAMP(4);
        if (layer == 1) {
            const int mb = blockIdx.x >> 3, cg = blockIdx.x & 7;
            const bf16* src = g_yT + (size_t)(cg * 80 + (tid >> 4)) * XCP + mb * 128 + (tid & 15) * 8;
            uint32_t v[3][4];
            __syncthreads();
            TSTAMP(5);
            uint32_t todo = warp < 8 ? 7 : 3;
#pragma unroll 1
            for (int it = 0; it < SPIN_MAX; it++) {
#pragma unroll
                for (int k = 0; k < 3; k++)
                    if (todo >> k & 1)
                        asm volatile("ld.relaxed.gpu.global.v4.u32 {%0,%1,%2,%3}, [%4];" : "=r"(v[k][0]), "=r"(v[k][1]), "=r"(v[k][2]), "=r"(v[k][3]) : "l"(src + k * (32 * XCP)) : "memory");
#pragma unroll
                for (int k = 0; k < 3; k++)
                    if ((todo >> k & 1) && v[k][0] != ~0u && v[k][1] != ~0u && v[k][2] != ~0u && v[k][3] != ~0u) {
                        *reinterpret_cast<uint4*>(sm + (32 * k + (tid >> 4)) * 272 + (tid & 15) * 16) = make_uint4(v[k][0], v[k][1], v[k][2], v[k][3]);
                        todo ^= 1u << k;
                    }
                if (!todo) break;
                __nanosleep(CV_SLEEP);
            }
            __syncthreads();
            uint32_t w[12];
#pragma unroll
            for (int k = 0; k < 3; k++) ldsm_x4(&w[4 * k], smem_u32(sm) + min(32 * k + lane, 79) * 272 + warp * 16);
            const uint32_t ot = smem_u32(sm + CV_SM_O) + warp * 1280, oa = ot + (lane & 7) * 160 + (lane >> 3) * 16;
            stsm_x4_t(oa, w[0], w[1], w[2], w[3]);
            stsm_x4_t(oa + 64, w[4], w[5], w[6], w[7]);
            asm volatile("stmatrix.sync.aligned.m8n8.x2.trans.shared.b16 [%0], {%1,%2};" ::"r"(oa + 128), "r"(w[8]), "r"(w[9]) : "memory");
            fence_async_smem();
            __syncwarp();
            if (lane == 0) tma_store_2d(&tmOut, cg * 80, mb * 128 + 8 * warp, ot);
        }
    }
    TSTAMP(3);
    GSTAMP(g_tim, 14);
    SPAN(3 + 4 * layer, 3);
}

__device__ __forceinline__ void wgmma_fence() { asm volatile("wgmma.fence.sync.aligned;" ::: "memory"); }
__device__ __forceinline__ void wgmma_commit() { asm volatile("wgmma.commit_group.sync.aligned;" ::: "memory"); }
template <int N> __device__ __forceinline__ void wgmma_wait() { asm volatile("wgmma.wait_group.sync.aligned %0;" ::"n"(N) : "memory"); }
__device__ __forceinline__ uint64_t make_desc(uint32_t addr, uint32_t lbo, uint32_t sbo, uint32_t mode) {
    return (uint64_t)((addr & 0x3FFFF) >> 4) | ((uint64_t)(lbo >> 4) << 16) | ((uint64_t)(sbo >> 4) << 32) | ((uint64_t)mode << 62);
}
template <int TA, int TB>
__device__ __forceinline__ void wgmma_n240(float (&d)[120], uint64_t da, uint64_t db) {
    asm volatile("wgmma.mma_async.sync.aligned.m64n240k16.f32.bf16.bf16 {%0,%1,%2,%3,%4,%5,%6,%7,%8,%9,%10,%11,%12,%13,%14,%15,%16,%17,%18,%19,%20,%21,%22,%23,%24,%25,%26,%27,%28,%29,%30,%31,%32,%33,%34,%35,%36,%37,%38,%39,%40,%41,%42,%43,%44,%45,%46,%47,%48,%49,%50,%51,%52,%53,%54,%55,%56,%57,%58,%59,%60,%61,%62,%63,%64,%65,%66,%67,%68,%69,%70,%71,%72,%73,%74,%75,%76,%77,%78,%79,%80,%81,%82,%83,%84,%85,%86,%87,%88,%89,%90,%91,%92,%93,%94,%95,%96,%97,%98,%99,%100,%101,%102,%103,%104,%105,%106,%107,%108,%109,%110,%111,%112,%113,%114,%115,%116,%117,%118,%119}, %120, %121, 1, 1, 1, %122, %123;"
                 : "+f"(d[0]), "+f"(d[1]), "+f"(d[2]), "+f"(d[3]), "+f"(d[4]), "+f"(d[5]), "+f"(d[6]), "+f"(d[7]), "+f"(d[8]), "+f"(d[9]), "+f"(d[10]), "+f"(d[11]), "+f"(d[12]), "+f"(d[13]), "+f"(d[14]), "+f"(d[15]), "+f"(d[16]), "+f"(d[17]), "+f"(d[18]), "+f"(d[19]), "+f"(d[20]), "+f"(d[21]), "+f"(d[22]), "+f"(d[23]), "+f"(d[24]), "+f"(d[25]), "+f"(d[26]), "+f"(d[27]), "+f"(d[28]), "+f"(d[29]), "+f"(d[30]), "+f"(d[31]), "+f"(d[32]), "+f"(d[33]), "+f"(d[34]), "+f"(d[35]), "+f"(d[36]), "+f"(d[37]), "+f"(d[38]), "+f"(d[39]), "+f"(d[40]), "+f"(d[41]), "+f"(d[42]), "+f"(d[43]), "+f"(d[44]), "+f"(d[45]), "+f"(d[46]), "+f"(d[47]), "+f"(d[48]), "+f"(d[49]), "+f"(d[50]), "+f"(d[51]), "+f"(d[52]), "+f"(d[53]), "+f"(d[54]), "+f"(d[55]), "+f"(d[56]), "+f"(d[57]), "+f"(d[58]), "+f"(d[59]), "+f"(d[60]), "+f"(d[61]), "+f"(d[62]), "+f"(d[63]), "+f"(d[64]), "+f"(d[65]), "+f"(d[66]), "+f"(d[67]), "+f"(d[68]), "+f"(d[69]), "+f"(d[70]), "+f"(d[71]), "+f"(d[72]), "+f"(d[73]), "+f"(d[74]), "+f"(d[75]), "+f"(d[76]), "+f"(d[77]), "+f"(d[78]), "+f"(d[79]), "+f"(d[80]), "+f"(d[81]), "+f"(d[82]), "+f"(d[83]), "+f"(d[84]), "+f"(d[85]), "+f"(d[86]), "+f"(d[87]), "+f"(d[88]), "+f"(d[89]), "+f"(d[90]), "+f"(d[91]), "+f"(d[92]), "+f"(d[93]), "+f"(d[94]), "+f"(d[95]), "+f"(d[96]), "+f"(d[97]), "+f"(d[98]), "+f"(d[99]), "+f"(d[100]), "+f"(d[101]), "+f"(d[102]), "+f"(d[103]), "+f"(d[104]), "+f"(d[105]), "+f"(d[106]), "+f"(d[107]), "+f"(d[108]), "+f"(d[109]), "+f"(d[110]), "+f"(d[111]), "+f"(d[112]), "+f"(d[113]), "+f"(d[114]), "+f"(d[115]), "+f"(d[116]), "+f"(d[117]), "+f"(d[118]), "+f"(d[119])
                 : "l"(da), "l"(db), "n"(TA), "n"(TB));
}

template <int TA, int TB>
__device__ __forceinline__ void wgmma_n80(float (&d)[40], uint64_t da, uint64_t db) {
    asm volatile("wgmma.mma_async.sync.aligned.m64n80k16.f32.bf16.bf16 {%0,%1,%2,%3,%4,%5,%6,%7,%8,%9,%10,%11,%12,%13,%14,%15,%16,%17,%18,%19,%20,%21,%22,%23,%24,%25,%26,%27,%28,%29,%30,%31,%32,%33,%34,%35,%36,%37,%38,%39}, %40, %41, 1, 1, 1, %42, %43;"
                 : "+f"(d[0]), "+f"(d[1]), "+f"(d[2]), "+f"(d[3]), "+f"(d[4]), "+f"(d[5]), "+f"(d[6]), "+f"(d[7]), "+f"(d[8]), "+f"(d[9]), "+f"(d[10]), "+f"(d[11]), "+f"(d[12]), "+f"(d[13]), "+f"(d[14]), "+f"(d[15]), "+f"(d[16]), "+f"(d[17]), "+f"(d[18]), "+f"(d[19]), "+f"(d[20]), "+f"(d[21]), "+f"(d[22]), "+f"(d[23]), "+f"(d[24]), "+f"(d[25]), "+f"(d[26]), "+f"(d[27]), "+f"(d[28]), "+f"(d[29]), "+f"(d[30]), "+f"(d[31]), "+f"(d[32]), "+f"(d[33]), "+f"(d[34]), "+f"(d[35]), "+f"(d[36]), "+f"(d[37]), "+f"(d[38]), "+f"(d[39])
                 : "l"(da), "l"(db), "n"(TA), "n"(TB));
}

constexpr int A1_THREADS = 384;
constexpr int A1_NST = 4;
#define A1_PRE0 2
#define A1_SDELAY 1
#define A1_PRE1 1
constexpr int A1_STAGE = 16384 + WQ_STAGE;
constexpr int A1_KVP = 336;
constexpr int A1_SM_KV = 2 * A1_STAGE;
constexpr int A1_SM_O = A1_SM_KV + 144 * A1_KVP;
constexpr int A1_SM_R = A1_NST * A1_STAGE;
constexpr int A1_SM_BAR = A1_SM_R + 20480;
constexpr int A1_SM_CS = A1_SM_BAR + 256;
constexpr int A1_SM_RS = A1_SM_CS + 1024;
constexpr int A1_SM_RED = A1_SM_RS + 1024;
constexpr int A1_SMEM = A1_SM_RED + 1152 + 1024;
static_assert(A1_SM_O % 128 == 0 && A1_SM_O + 20480 <= A1_SM_R, "layout");

template <int L>
__device__ __forceinline__ void a1_mainloop(float (&acc)[120], uint32_t sbase, uint32_t bars, int wg, int tile) {
    constexpr int layer = L; (void)layer;
    const uint64_t da0 = L ? make_desc(sbase + wg * 8192, 8192, 1024, 1) : make_desc(sbase + wg * 8192, 16, 1024, 1), db0 = make_desc(sbase + 16384, 16, 1024, 1);
#pragma unroll 1
    for (int t = 0; t < 10; t++) {
        const int st = t % A1_NST;
        mbar_wait(bars + 8 * st, (t / A1_NST) & 1);
        TSTAMP3(1 + t);
        wgmma_fence();
#pragma unroll
        for (int kk = 0; kk < 4; kk++) wgmma_n240<L, 0>(acc, da0 + (uint32_t)(st * (A1_STAGE / 16) + kk * (L ? 128 : 2)), db0 + (uint32_t)(st * (A1_STAGE / 16) + kk * 2));
        wgmma_commit();
        wgmma_wait<1>();
        if (t > 0 && (threadIdx.x & 127) == 0) mbar_arrive(t < 9 ? bars + 8 * (A1_NST + (t - 1) % A1_NST) : bars + 144);
    }
}

__global__ void __launch_bounds__(A1_THREADS, 1) a1_kernel(const int layer, const bf16* __restrict__ x0, const __grid_constant__ CUtensorMap tmX,
                                                           const __grid_constant__ CUtensorMap tmR, const __grid_constant__ CUtensorMap tmOst) {
    extern __shared__ unsigned char smraw[];
    const uint32_t sbase = (smem_u32(smraw) + 1023) & ~1023u;
    const uint32_t bars = sbase + A1_SM_BAR;
    const uint32_t bar_stat = bars + 64, bar_kv = bars + 72, bar_r = bars + 152;
    const int tid = threadIdx.x, w = __shfl_sync(~0u, tid >> 5, 0), wg = w >> 2;
    const int tile = sm_tile();
    if (tile >= 128) { sm_idle(2 * layer); return; }
    const int mb = (tile >> 2) & 15, hg = 4 * (tile >> 6) + (tile & 3);
    unsigned char* stg = smraw + (sbase - smem_u32(smraw));
    float* cs = reinterpret_cast<float*>(stg + A1_SM_CS);
    float2* rst = reinterpret_cast<float2*>(stg + A1_SM_RS);
    const int pre = layer ? A1_PRE1 : A1_PRE0;
    auto issue_w = [&](int kb) {
        bulk_load(sbase + (kb % A1_NST) * A1_STAGE + 16384, reinterpret_cast<const unsigned char*>(g_wq) + (hg * 10 + kb) * WQ_STAGE, WQ_STAGE, bars + 8 * (kb % A1_NST));
    };
    auto issue_x = [&](int kb) {
        const uint32_t dst = sbase + (kb % A1_NST) * A1_STAGE, full = bars + 8 * (kb % A1_NST);
        if (layer == 0) tma_load_2d(dst, &tmX, kb * 64, mb * 128, full);
        else { tma_load_2d(dst, &tmX, mb * 128, kb * 64, full); tma_load_2d(dst + 8192, &tmX, mb * 128 + 64, kb * 64, full); }
    };
    if (w == 8) {
        if (tid == 256) {
            prefetch_tmap(&tmX);
#pragma unroll
            for (int i = 0; i < A1_NST; i++) { mbar_init(bars + 8 * i, 1); mbar_init(bars + 8 * (A1_NST + i), 2); }
            mbar_init(bar_r, 1);
            asm volatile("fence.mbarrier_init.release.cluster;" ::: "memory");
#pragma unroll
            for (int i = 0; i < A1_NST; i++) mbar_expect_tx(bars + 8 * i, A1_STAGE);
            mbar_expect_tx(bar_r, 20480);
        }
        __syncwarp();
        asm volatile("bar.arrive 0, 384;" ::: "memory");
        if (tid == 256) {
#pragma unroll 1
            for (int kb = 0; kb < pre; kb++) { if (layer) issue_w(kb); else issue_x(kb); }
            pdl_sync();
#pragma unroll 1
            for (int kb = 0; kb < A1_NST; kb++) {
                if (kb == A1_SDELAY && layer) {
                    tma_load_2d(sbase + A1_SM_R, &tmR, mb * 128, hg * 80, bar_r); tma_load_2d(sbase + A1_SM_R + 10240, &tmR, mb * 128 + 64, hg * 80, bar_r);
                }
                if (kb >= pre || layer) issue_x(kb);
                if (kb >= pre || !layer) issue_w(kb);
            }
        }
    } else {
        if (tid == 0) {
            mbar_init(bar_stat, 4);
#pragma unroll
            for (int i = 0; i < 9; i++) mbar_init(bar_kv + 8 * i, i ? 1 : 4);
            mbar_init(bars + 144, 2);
            asm volatile("fence.mbarrier_init.release.cluster;" ::: "memory");
        } else if (tid == 320) { prefetch_tmap(&tmR); prefetch_tmap(&tmOst); }
        asm volatile("bar.sync 0, 384;" ::: "memory");
    }
    SPAN(1 + 4 * layer, 0);
    const uint32_t tag = ld_epoch();
    if (tid == 352) sm_started(2 * layer);
    if (wg == 2) {
        const bool is_producer = (tid == 256);
        const int t = tid - 256;
        if (layer && w > 8) pdl_sync();
        if (tid >= 288) {
            const int j = tid - 288;
            if (layer == 0) {
                float* red = reinterpret_cast<float*>(stg + A1_SM_RED);
                const int r = j / 6, c6 = j - 6 * r;
                const uint4* src = reinterpret_cast<const uint4*>(x0 + (size_t)(mb * 128 + hg * 16 + r) * DM);
                uint4 v[14];
#pragma unroll
                for (int k = 0; k < 14; k++) v[k] = __ldg(src + min(c6 + 6 * k, 79));
                const float p0 = __uint_as_float(__ldg(reinterpret_cast<const uint32_t*>(src)) << 16);
                float s[2] = {0.f, 0.f}, q[2] = {0.f, 0.f};
#pragma unroll
                for (int k = 0; k < 14; k++) {
                    const uint32_t w[4] = {v[k].x, v[k].y, v[k].z, v[k].w};
                    if (k < 13 || c6 < 2) {
#pragma unroll
                        for (int i = 0; i < 4; i++) {
                            const float a = __uint_as_float(w[i] << 16) - p0, b = __uint_as_float(w[i] & 0xffff0000u) - p0;
                            s[0] += a; s[1] += b; q[0] = fmaf(a, a, q[0]); q[1] = fmaf(b, b, q[1]);
                        }
                    }
                }
                red[j] = s[0] + s[1]; red[96 + j] = q[0] + q[1]; red[192 + j] = p0;
                asm volatile("bar.sync 2, 96;" ::: "memory");
                if (j < 16) {
                    float s0 = 0.f, q0 = 0.f;
#pragma unroll
                    for (int k = 0; k < 6; k++) { s0 += red[6 * j + k]; q0 += red[96 + 6 * j + k]; }
                    const float d = s0 * (1.0f / DM);
                    const uint32_t ms = pack2(red[192 + 6 * j] + d, rbf(sqrtf(rbf(rbf(fmaxf(fmaf(-d, d, q0 * (1.0f / DM)), 0.f)) + 1e-5f))));
                    asm volatile("st.global.cg.u64 [%0], %1;" ::"l"(g_rstat + mb * 128 + hg * 16 + j), "l"(tagw(ms, tag)) : "memory");
                    g_piv[mb * 128 + hg * 16 + j] = __ushort_as_bfloat16((unsigned short)ms);
                }
                pdl_sync();
            } else if (j >= 32) {
                const int ch = j & 7, kg = (j >> 3) & 3;
                const unsigned char* src = stg + A1_SM_R + ((j >> 5) - 1) * 10240;
                mbar_wait(bar_r, 0);
                uint4 v[20];
#pragma unroll
                for (int k = 0; k < 20; k++) v[k] = *reinterpret_cast<const uint4*>(src + (4 * k + kg) * 128 + ((ch ^ ((4 * k + kg) & 7)) << 4));
                const uint4 pv = *reinterpret_cast<const uint4*>(src + (ch << 4));
                float s[8], q[8], p0[8] = {__uint_as_float(pv.x << 16), __uint_as_float(pv.x & 0xffff0000u), __uint_as_float(pv.y << 16), __uint_as_float(pv.y & 0xffff0000u),
                                           __uint_as_float(pv.z << 16), __uint_as_float(pv.z & 0xffff0000u), __uint_as_float(pv.w << 16), __uint_as_float(pv.w & 0xffff0000u)};
#pragma unroll
                for (int i = 0; i < 8; i++) { s[i] = 0.f; q[i] = 0.f; }
#pragma unroll
                for (int k = 0; k < 20; k++) {
                    const uint32_t w[4] = {v[k].x, v[k].y, v[k].z, v[k].w};
#pragma unroll
                    for (int i = 0; i < 4; i++) {
                        const float a = __uint_as_float(w[i] << 16) - p0[2 * i], b = __uint_as_float(w[i] & 0xffff0000u) - p0[2 * i + 1];
                        s[2 * i] += a; s[2 * i + 1] += b; q[2 * i] = fmaf(a, a, q[2 * i]); q[2 * i + 1] = fmaf(b, b, q[2 * i + 1]);
                    }
                }
#pragma unroll
                for (int i = 0; i < 4; i++) {
                    const bool up = kg & 2;
                    const float ss = __shfl_xor_sync(~0u, up ? s[i] : s[i + 4], 16), qq = __shfl_xor_sync(~0u, up ? q[i] : q[i + 4], 16);
                    s[i] = (up ? s[i + 4] : s[i]) + ss; q[i] = (up ? q[i + 4] : q[i]) + qq; p0[i] = up ? p0[i + 4] : p0[i];
                }
#pragma unroll
                for (int i = 0; i < 2; i++) {
                    const bool up = kg & 1;
                    const float ss = __shfl_xor_sync(~0u, up ? s[i] : s[i + 2], 8), qq = __shfl_xor_sync(~0u, up ? q[i] : q[i + 2], 8);
                    s[i] = (up ? s[i + 2] : s[i]) + ss; q[i] = (up ? q[i + 2] : q[i]) + qq; p0[i] = up ? p0[i + 2] : p0[i];
                }
#pragma unroll
                for (int r = 0; r < 2; r++) {
                    const float d = s[r] * (1.0f / 80.0f);
                    st_tag2(g_part + (mb * 8 + hg) * 128 + 64 * r + j - 32, __float_as_uint(p0[r] + d), __float_as_uint(fmaxf(fmaf(-d, s[r], q[r]), 0.f)), tag);
                }
            }
            TSTAMP1T(12, 320);
            if (j < 32) {
#pragma unroll
                for (int h = 0; h < 2; h++) {
                    const int i = j + 32 * h;
                    if (i < 60) {
                        float4 a = make_float4(0.f, 0.f, 0.f, 0.f);
#pragma unroll
                        for (int k = 0; k < 10; k++) {
                            const float4 v = __ldcg(reinterpret_cast<const float4*>(g_csp + k * 1920 + hg * 240) + i);
                            a.x += v.x; a.y += v.y; a.z += v.z; a.w += v.w;
                        }
                        reinterpret_cast<float4*>(cs)[i] = a;
                    }
                }
                TSTAMP1T(13, 288);
            } else if (layer == 0) {
                ulonglong2 v;
#pragma unroll 1
                for (int it = 0; it < SPIN_MAX; it++) {
                    v = ld_tag2(reinterpret_cast<const ulonglong2*>(g_rstat + mb * 128) + j - 32);
                    if (tag_ok(v, tag)) break;
                    __nanosleep(100);
                }
                *reinterpret_cast<float4*>(rst + 2 * (j - 32)) = make_float4(__uint_as_float((uint32_t)v.x << 16), __frcp_rn(__uint_as_float((uint32_t)v.x & 0xffff0000u)),
                                                                             __uint_as_float((uint32_t)v.y << 16), __frcp_rn(__uint_as_float((uint32_t)v.y & 0xffff0000u)));
            } else {
                const ulonglong2* gp = g_part + mb * 8 * 128 + j - 32;
#pragma unroll 1
                for (int it = 0; it < SPIN_MAX; it++) {
                    if (__all_sync(~0u, tag_ok(ld_tag2(gp + (j & 7) * 128 + 64), tag))) break;
                    __nanosleep(200);
                }
                ulonglong2 pv[16];
#pragma unroll 1
                for (int it = 0; it < SPIN_MAX; it++) {
                    bool ok = true;
#pragma unroll
                    for (int k = 0; k < 16; k++) pv[k] = ld_tag2(gp + k * 64);
#pragma unroll
                    for (int k = 0; k < 16; k++) ok = ok && tag_ok(pv[k], tag);
                    if (ok) break;
                    __nanosleep(200);
                }
                float o[4];
#pragma unroll
                for (int r = 0; r < 2; r++) {
                    float mean = 0.f, m2 = 0.f;
#pragma unroll
                    for (int k = 0; k < 8; k++) mean += __uint_as_float((uint32_t)pv[2 * k + r].x);
                    mean *= 0.125f;
#pragma unroll
                    for (int k = 0; k < 8; k++) {
                        const float dm = __uint_as_float((uint32_t)pv[2 * k + r].x) - mean;
                        m2 += fmaf(80.0f * dm, dm, __uint_as_float((uint32_t)pv[2 * k + r].y));
                    }
                    o[2 * r] = rbf(mean);
                    o[2 * r + 1] = __frcp_rn(rbf(sqrtf(rbf(rbf(m2 * (1.0f / DM)) + 1e-5f))));
                }
                const int row = ((j >> 5) - 1) * 64 + (j & 7) * 8 + ((j >> 3) & 3) * 2;
                *reinterpret_cast<float4*>(rst + row) = make_float4(o[0], o[1], o[2], o[3]);
                if (hg == 0) *reinterpret_cast<uint32_t*>(g_piv + SEQ + mb * 128 + row) = __byte_perm(__float_as_uint(o[0]), __float_as_uint(o[2]), 0x7632);
            }
            TSTAMP1T(7, 320);
        } else if (is_producer) {
            for (int kb = A1_NST; kb < 10; kb++) {
                mbar_wait(bars + 8 * (A1_NST + kb % A1_NST), ((kb / A1_NST) - 1) & 1);
                mbar_expect_tx(bars + 8 * (kb % A1_NST), A1_STAGE);
                issue_x(kb); issue_w(kb);
            }
            TSTAMP1T(6, 256);
        }
        __syncwarp();
        if ((tid & 31) == 0) mbar_arrive(bar_stat);
        mbar_wait(bars + 144, 0);
        mbar_wait(bars + 8 * (A1_NST + 3), 1);
        TSTAMP1T(9, 256);
        const ulonglong2* hin = g_halo + ((size_t)(layer * 16 + mb - 1) * 8 + hg) * 640 + t;
        ulonglong2 hv[5];
        if (mb > 0) {
#pragma unroll 1
            for (int it = 0; it < SPIN_MAX; it++) {
                bool ok = true;
#pragma unroll
                for (int k = 0; k < 5; k++) hv[k] = ld_tag2(hin + 128 * k);
#pragma unroll
                for (int k = 0; k < 5; k++) ok = ok && tag_ok(hv[k], tag);
                if (ok) break;
            }
        } else {
#pragma unroll
            for (int k = 0; k < 5; k++) hv[k] = make_ulonglong2(0, 0);
        }
        TSTAMP1T(11, 256);
        unsigned char* hd = stg + A1_SM_KV + ((t & 31) >> 2) * A1_KVP + (t & 3) * 4 + (t >> 5) * 16;
#pragma unroll
        for (int k = 0; k < 5; k++) {
            *reinterpret_cast<uint32_t*>(hd + 64 * k) = (uint32_t)hv[k].x;
            *reinterpret_cast<uint32_t*>(hd + 64 * k + 8 * A1_KVP) = (uint32_t)hv[k].y;
        }
        __syncwarp();
        if ((tid & 31) == 0) mbar_arrive(bar_kv);
    } else {
        pdl_sync();
        SPAN(1 + 4 * layer, 1);
        TSTAMP1(0);
        if (threadIdx.x == 0) { GSTAMP(g_tim1, 15); }
        TSTAMP3(0);
        float acc[120];
#pragma unroll
        for (int i = 0; i < 120; i++) acc[i] = 0.f;
        if (layer == 0) a1_mainloop<0>(acc, sbase, bars, wg, tile); else a1_mainloop<1>(acc, sbase, bars, wg, tile);
        const int lane = tid & 31, warp = w, g = lane >> 2, t = lane & 3;
        mbar_wait(bar_stat, 0);
        mbar_wait(bars + 8 * (A1_NST + 3), 1);
        const float2 sa_ = rst[16 * warp + g], sb_ = rst[16 * warp + g + 8];
        wgmma_wait<0>();
        TSTAMP1(2);
        uint32_t f[30][2];
        auto norm = [&](int j0) {
            float2 cc[10];
#pragma unroll
            for (int j = 0; j < 10; j++) cc[j] = *reinterpret_cast<const float2*>(cs + 8 * (j0 + j) + 2 * t);
#pragma unroll
            for (int j = 0; j < 10; j++) {
                const float* a = acc + 4 * (j0 + j);
                f[j0 + j][0] = pack2(fmaf(-sa_.x, cc[j].x, a[0]) * sa_.y, fmaf(-sa_.x, cc[j].y, a[1]) * sa_.y);
                f[j0 + j][1] = pack2(fmaf(-sb_.x, cc[j].x, a[2]) * sb_.y, fmaf(-sb_.x, cc[j].y, a[3]) * sb_.y);
            }
        };
        norm(10); norm(20);
        if (warp == 7) {
            ulonglong2* hout = g_halo + ((size_t)(layer * 16 + mb) * 8 + hg) * 640 + lane;
#pragma unroll
            for (int j = 0; j < 20; j++) st_tag2(hout + 32 * j, f[10 + j][0], f[10 + j][1], tag);
        }
        const uint32_t kvw = sbase + A1_SM_KV + 16 * warp * A1_KVP;
        const uint32_t mrow = kvw + (lane & 15) * A1_KVP + (lane >> 4) * 16;
#pragma unroll
        for (int j = 0; j < 20; j += 2) stsm_x4(mrow + 16 * A1_KVP + 16 * j, f[10 + j][0], f[10 + j][1], f[11 + j][0], f[11 + j][1]);
        __syncwarp();
        if (lane == 0) mbar_arrive(bar_kv + 8 * (warp + 1));
        norm(0);
        TSTAMP1T(10, 64);
        float sc[4][4][4];
        uint32_t qs[4][2];
#pragma unroll
        for (int h = 0; h < 4; h++) {
            const int jb = 5 * (h >> 1) + 3 * (h & 1), js = 5 * (h >> 1) + 2;
            qs[h][0] = (t >> 1) == (h & 1) ? f[js][0] : 0u; qs[h][1] = (t >> 1) == (h & 1) ? f[js][1] : 0u;
#pragma unroll
            for (int nt = 2; nt < 4; nt++) {
#pragma unroll
                for (int e = 0; e < 4; e++) sc[h][nt][e] = 0.f;
                mma_bf16(sc[h][nt], f[jb][0], f[jb][1], f[jb + 1][0], f[jb + 1][1], f[10 + jb][nt - 2], f[11 + jb][nt - 2]);
                mma_bf16_k8(sc[h][nt], qs[h][0], qs[h][1], f[10 + js][nt - 2]);
            }
        }
        mbar_wait(bar_kv + 8 * warp, 0);
        TSTAMP1(8);
        uint32_t kp[10][2];
#pragma unroll
        for (int j = 0; j < 10; j += 2) ldsm_x4(&kp[j][0], mrow + 16 * j);
#pragma unroll
        for (int h = 0; h < 4; h++) {
            const int jb = 5 * (h >> 1) + 3 * (h & 1), js = 5 * (h >> 1) + 2;
#pragma unroll
            for (int nt = 0; nt < 2; nt++) {
#pragma unroll
                for (int e = 0; e < 4; e++) sc[h][nt][e] = 0.f;
                mma_bf16(sc[h][nt], f[jb][0], f[jb][1], f[jb + 1][0], f[jb + 1][1], kp[jb][nt], kp[jb + 1][nt]);
                mma_bf16_k8(sc[h][nt], qs[h][0], qs[h][1], kp[js][nt]);
            }
        }
        uint32_t vb[10][4];
#pragma unroll
        for (int j = 0; j < 10; j++) ldsm_x4_t(vb[j], kvw + lane * A1_KVP + 160 + 16 * j);
        TSTAMP1T(3, 64);
        const bool odd = g & 1, hi = t > (g >> 1), edge = (mb | warp) == 0;
        float p[4][4], mx[4][2], sum[4][2];
#pragma unroll
        for (int h = 0; h < 4; h++) {
#pragma unroll
            for (int r = 0; r < 2; r++) {
                const float a = odd ? sc[h][1 + r][2 * r + 1] : sc[h][1 + r][2 * r];
                const float b0 = odd ? sc[h][r][2 * r + 1] : sc[h][r][2 * r], b1 = odd ? sc[h][2 + r][2 * r + 1] : sc[h][2 + r][2 * r];
                const uint32_t w = pack2(a, hi ? b0 : b1);
                const uint32_t w2 = pack2(__uint_as_float(w << 16) * 0.22360679774997896f, __uint_as_float(w & 0xffff0000u) * 0.22360679774997896f);
                p[h][2 * r] = __uint_as_float(w2 << 16); p[h][2 * r + 1] = __uint_as_float(w2 & 0xffff0000u);
            }
            if (edge) {
                p[h][0] = -1.0e9f;
                if (hi) { p[h][1] = -1.0e9f; p[h][3] = -1.0e9f; }
            }
            mx[h][0] = fmaxf(p[h][0], p[h][1]); mx[h][1] = fmaxf(p[h][2], p[h][3]);
        }
#pragma unroll
        for (int o = 1; o <= 2; o <<= 1)
#pragma unroll
            for (int h = 0; h < 4; h++)
#pragma unroll
                for (int r = 0; r < 2; r++) mx[h][r] = fmaxf(mx[h][r], __shfl_xor_sync(~0u, mx[h][r], o));
#pragma unroll
        for (int h = 0; h < 4; h++)
#pragma unroll
            for (int r = 0; r < 2; r++) {
                p[h][2 * r] = __expf(p[h][2 * r] - mx[h][r]); p[h][2 * r + 1] = __expf(p[h][2 * r + 1] - mx[h][r]);
                sum[h][r] = p[h][2 * r] + p[h][2 * r + 1];
            }
#pragma unroll
        for (int o = 1; o <= 2; o <<= 1)
#pragma unroll
            for (int h = 0; h < 4; h++)
#pragma unroll
                for (int r = 0; r < 2; r++) sum[h][r] += __shfl_xor_sync(~0u, sum[h][r], o);
        TSTAMP1T(5, 64);
        const uint32_t selA = odd ? 0x1044u : 0x4410u, selB = odd ? 0x3244u : 0x4432u, selH = hi ? selB : 0x4444u, selL = hi ? 0x4444u : selB;
        const uint32_t orow = sbase + A1_SM_O + (16 * warp + (lane & 15)) * 160 + (lane >> 4) * 16;
        uint32_t ob[10][2];
#pragma unroll
        for (int P = 0; P < 2; P++) {
            float os[2][4];
#pragma unroll
            for (int e = 0; e < 2; e++) {
                const int h = 2 * P + e;
                const float i0 = __fdividef(1.0f, sum[h][0]), i1 = __fdividef(1.0f, sum[h][1]);
                const uint32_t w0 = pack2(p[h][0] * i0, p[h][1] * i0), w1 = pack2(p[h][2] * i1, p[h][3] * i1);
                const uint32_t a00 = __byte_perm(w0, 0, selH), a02 = __byte_perm(w0, 0, selA), a03 = __byte_perm(w1, 0, selH);
                const uint32_t a10 = __byte_perm(w0, 0, selL), a11 = __byte_perm(w1, 0, selA), a13 = __byte_perm(w1, 0, selL);
#pragma unroll
                for (int dt = 0; dt < 3; dt++) {
                    const int j = 5 * P + (dt < 2 ? 3 * e + dt : 2);
                    float o[4] = {0.f, 0.f, 0.f, 0.f};
                    mma_bf16(o, a00, 0u, a02, a03, vb[j][0], vb[j][1]);
                    mma_bf16(o, a10, a11, 0u, a13, vb[j][2], vb[j][3]);
                    if (dt < 2) { ob[j][0] = pack2(o[0], o[1]); ob[j][1] = pack2(o[2], o[3]); }
                    else { os[e][0] = o[0]; os[e][1] = o[1]; os[e][2] = o[2]; os[e][3] = o[3]; }
                }
            }
            ob[5 * P + 2][0] = t < 2 ? pack2(os[0][0], os[0][1]) : pack2(os[1][0], os[1][1]);
            ob[5 * P + 2][1] = t < 2 ? pack2(os[0][2], os[0][3]) : pack2(os[1][2], os[1][3]);
        }
#pragma unroll
        for (int j = 0; j < 10; j += 2) stsm_x4(orow + 16 * j, ob[j][0], ob[j][1], ob[j + 1][0], ob[j + 1][1]);
        fence_async_smem();
        __syncwarp();
        if (lane == 0) tma_store_2d(&tmOst, hg * 80, mb * 128 + 16 * warp, sbase + A1_SM_O + 16 * warp * 160);
        TSTAMP1T(4, 64);
        TSTAMP1(1);
        GSTAMP(g_tim1, 14);
        SPAN(1 + 4 * layer, 3);
    }
}

constexpr int A2_THREADS = 288;
constexpr int A2_NA = 6;
constexpr int A2_WPRE = 4;
constexpr int A2_SM_A = 10 * WO_STAGE;
constexpr int A2_SM_R = A2_SM_A + A2_NA * 16384;
constexpr int A2_SM_BAR = A2_SM_R + 20480;
constexpr int A2_SMEM = A2_SM_BAR + 256 + 1024;

__global__ void __launch_bounds__(A2_THREADS, 1) a2_kernel(const int layer, const __grid_constant__ CUtensorMap tmO, const __grid_constant__ CUtensorMap tmR,
                                                           const __grid_constant__ CUtensorMap tmX1) {
    extern __shared__ unsigned char smraw[];
    const uint32_t sbase = (smem_u32(smraw) + 1023) & ~1023u;
    const uint32_t bars = sbase + A2_SM_BAR, bar_e = bars + 80, bar_r = bars + 128, bar_w = bars + 136;
    const int tid = threadIdx.x, w = __shfl_sync(~0u, tid >> 5, 0), wg = w >> 2;
    const int tile = sm_tile();
    if (tile >= 128) { sm_idle(2 * layer + 1); return; }
    const int mb = tile >> 3, cg = tile & 7;
    if (wg == 2) {
        if (tid == 256) {
            prefetch_tmap(&tmO);
#pragma unroll
            for (int i = 0; i < 19; i++) mbar_init(bars + 8 * i, i >= 10 && i < 16 ? 2 : 1);
            asm volatile("fence.mbarrier_init.release.cluster;" ::: "memory");
            mbar_expect_tx(bar_w, A2_WPRE * WO_STAGE);
            bulk_load(sbase, reinterpret_cast<const unsigned char*>(g_wo) + cg * 10 * WO_STAGE, A2_WPRE * WO_STAGE, bar_w);
        }
        __syncwarp();
        asm volatile("bar.arrive 0, 288;" ::: "memory");
        if (tid == 256) {
#pragma unroll
            for (int kb = 0; kb < 10; kb++) mbar_expect_tx(bars + 8 * kb, 16384);
            mbar_expect_tx(bar_w + 8, (10 - A2_WPRE) * WO_STAGE);
            mbar_expect_tx(bar_r, 20480);
            pdl_sync();
#pragma unroll 1
            for (int kb = 0; kb < 10; kb++) {
                if (kb >= A2_NA) mbar_wait(bar_e + 8 * (kb - A2_NA), 0);
                tma_load_2d(sbase + A2_SM_A + (kb < A2_NA ? kb : kb - A2_NA) * 16384, &tmO, kb * 64, mb * 128, bars + 8 * kb);
                if (kb == 2) bulk_load(sbase + A2_WPRE * WO_STAGE, reinterpret_cast<const unsigned char*>(g_wo) + (cg * 10 + A2_WPRE) * WO_STAGE, (10 - A2_WPRE) * WO_STAGE, bar_w + 8);
                if (kb == A2_NA - 1) {
                    if (layer == 0) tma_load_2d(sbase + A2_SM_R, &tmR, cg * 80, mb * 128, bar_r);
                    else { tma_load_2d(sbase + A2_SM_R, &tmR, mb * 128, cg * 80, bar_r); tma_load_2d(sbase + A2_SM_R + 10240, &tmR, mb * 128 + 64, cg * 80, bar_r); }
                }
            }
        }
    } else {
        if (tid == 224) { prefetch_tmap(&tmR); prefetch_tmap(&tmX1); sm_started(2 * layer + 1); }
        asm volatile("bar.sync 0, 288;" ::: "memory");
        SPAN(2 + 4 * layer, 0);
        pdl_sync();
        SPAN(2 + 4 * layer, 1);
        TSTAMP2(0);
        TSTAMP4(0);
        if (threadIdx.x == 0) { GSTAMP(g_tim2, 15); }
        const int lane = tid & 31, warp = w, g = lane >> 2, t = lane & 3;
        const int row = layer * SEQ + mb * 128 + 16 * warp + g;
        const unsigned short pv0 = __ldcg(reinterpret_cast<const unsigned short*>(g_piv) + row), pv1 = __ldcg(reinterpret_cast<const unsigned short*>(g_piv) + row + 8);
        float acc[40];
#pragma unroll
        for (int i = 0; i < 40; i++) acc[i] = 0.f;
        const uint64_t da0 = make_desc(sbase + A2_SM_A + wg * 8192, 16, 1024, 1), db0 = make_desc(sbase, 16, 1024, 1);
#pragma unroll 1
        for (int kb = 0; kb < 10; kb++) {
            if (kb == 0) TSTAMP4(11);
            if (kb == 0 || kb == A2_WPRE) mbar_wait(kb ? bar_w + 8 : bar_w, 0);
            mbar_wait(bars + 8 * kb, 0);
            TSTAMP4(1 + kb);
            wgmma_fence();
#pragma unroll
            for (int kk = 0; kk < 4; kk++) wgmma_n80<0, 0>(acc, da0 + (uint32_t)((kb < A2_NA ? kb : kb - A2_NA) * 1024 + kk * 2), db0 + (uint32_t)(kb * (WO_STAGE / 16) + kk * 2));
            wgmma_commit();
            wgmma_wait<1>();
            if (kb > 0 && kb <= A2_NA && (tid & 127) == 0) mbar_arrive(bar_e + 8 * (kb - 1));
        }
        const uint32_t trow = ((lane & 7) + 8 * (lane >> 4)) * 128 + (((2 * (warp & 3) + ((lane >> 3) & 1)) ^ (lane & 7)) << 4);
        uint32_t xr[10][2];
        mbar_wait(bar_r, 0);
        if (layer == 0) {
#pragma unroll
            for (int j = 0; j < 10; j += 2) ldsm_x4(&xr[j][0], sbase + A2_SM_R + (16 * warp + (lane & 15)) * 160 + (lane >> 4) * 16 + 16 * j);
        } else {
#pragma unroll
            for (int j = 0; j < 10; j += 2) ldsm_x4_t(&xr[j][0], sbase + A2_SM_R + wg * 10240 + trow + 1024 * j);
        }
        mbar_wait(bar_e + 8 * (4 + wg), 0);
        wgmma_wait<0>();
        TSTAMP2(1);
        const float p0 = __uint_as_float((uint32_t)pv0 << 16), p1 = __uint_as_float((uint32_t)pv1 << 16);
        float s[4] = {0.f, 0.f, 0.f, 0.f};
#pragma unroll
        for (int j = 0; j < 10; j++) {
#pragma unroll
            for (int hh = 0; hh < 2; hh++) {
                const uint32_t a = pack2(acc[4 * j + 2 * hh], acc[4 * j + 2 * hh + 1]);
                const __nv_bfloat162 r = __hadd2_rn(*reinterpret_cast<const __nv_bfloat162*>(&xr[j][hh]), *reinterpret_cast<const __nv_bfloat162*>(&a));
                const uint32_t w = *reinterpret_cast<const uint32_t*>(&r);
                xr[j][hh] = w;
                const float d0 = __uint_as_float(w << 16) - (hh ? p1 : p0), d1 = __uint_as_float(w & 0xffff0000u) - (hh ? p1 : p0);
                s[2 * hh] += d0 + d1;
                s[2 * hh + 1] = fmaf(d0, d0, fmaf(d1, d1, s[2 * hh + 1]));
            }
        }
        const uint32_t so = sbase + A2_SM_A + (4 + wg) * 16384;
#pragma unroll
        for (int j = 0; j < 10; j += 2) stsm_x4_t(so + trow + 1024 * j, xr[j][0], xr[j][1], xr[j + 1][0], xr[j + 1][1]);
        fence_async_smem();
        TSTAMP2(2);
#pragma unroll
        for (int o = 1; o <= 2; o <<= 1)
#pragma unroll
            for (int i = 0; i < 4; i++) s[i] += __shfl_xor_sync(~0u, s[i], o);
        if (t < 2) asm volatile("red.relaxed.gpu.global.add.v2.f32 [%0], {%1, %2};" ::"l"(g_sum + layer * SEQ + (g >> 1) * 512 + (mb * 16 + 2 * warp + t) * 2 + (g & 1)), "f"(t ? s[2] : s[0]), "f"(t ? s[3] : s[1]) : "memory");
        if (wg) asm volatile("bar.sync 2, 128;" ::: "memory"); else asm volatile("bar.sync 1, 128;" ::: "memory");
        TSTAMP2(3);
        if ((tid & 127) == 0) tma_store_2d(&tmX1, mb * 128 + 64 * wg, cg * 80, so);
        TSTAMP2(4);
        GSTAMP(g_tim2, 14);
        SPAN(2 + 4 * layer, 3);
    }
}

static int h_nsm;
static CUtensorMap h_tmX0, h_tmX1, h_tmOst, h_tmO, h_tmR0, h_tmR1, h_tmX1st, h_tmOut;
typedef CUresult (*PFN_encodeTiled)(CUtensorMap*, CUtensorMapDataType, cuuint32_t, void*, const cuuint64_t*, const cuuint64_t*,
                                    const cuuint32_t*, const cuuint32_t*, CUtensorMapInterleave, CUtensorMapSwizzle,
                                    CUtensorMapL2promotion, CUtensorMapFloatOOBfill);
static void make_tmap(CUtensorMap* tm, const void* ptr, uint64_t cols, uint64_t rows, uint32_t bc, uint32_t br, CUtensorMapSwizzle sw, uint64_t pitch = 0) {
    static PFN_encodeTiled fn = nullptr;
    if (!fn) {
        void* p = nullptr; cudaDriverEntryPointQueryResult qr;
        cudaGetDriverEntryPoint("cuTensorMapEncodeTiled", &p, cudaEnableDefault, &qr);
        fn = (PFN_encodeTiled)p;
    }
    cuuint64_t dims[2] = {cols, rows}; cuuint64_t strides[1] = {(pitch ? pitch : cols) * 2};
    cuuint32_t box[2] = {bc, br}; cuuint32_t es[2] = {1, 1};
    fn(tm, CU_TENSOR_MAP_DATA_TYPE_BFLOAT16, 2, const_cast<void*>(ptr), dims, strides, box, es, CU_TENSOR_MAP_INTERLEAVE_NONE, sw,
       CU_TENSOR_MAP_L2_PROMOTION_L2_128B, CU_TENSOR_MAP_FLOAT_OOB_FILL_NONE);
}
template <typename... Args>
static void launch_pdl(void (*kern)(Args...), int grid, int block, int smem, Args... args) {
    cudaLaunchConfig_t cfg = {};
    cfg.gridDim = dim3(grid); cfg.blockDim = dim3(block); cfg.dynamicSmemBytes = smem; cfg.stream = cudaStreamPerThread;
    cudaLaunchAttribute at[1];
    at[0].id = cudaLaunchAttributeProgrammaticStreamSerialization; at[0].val.programmaticStreamSerializationAllowed = 1;
    cfg.attrs = at; cfg.numAttrs = 1;
    cudaLaunchKernelEx(&cfg, kern, args...);
}
static void launch_stage(int k, void* const* d_in, void* d_out) {
    const KgIn kg = {(const bf16*)d_in[4], (const bf16*)d_in[5], (const bf16*)d_in[6], (const bf16*)d_in[7], (const bf16*)d_in[8], (const bf16*)d_in[0], (const bf16*)d_in[1], (const bf16*)d_in[2]};
    switch (k) {
        case 0: kgen_kernel<<<DM, KG_THREADS, 0, cudaStreamPerThread>>>(kg); break;
        case 1: launch_pdl(a1_kernel, h_nsm, A1_THREADS, A1_SMEM, 0, (const bf16*)d_in[0], h_tmX0, h_tmR1, h_tmOst); break;
        case 2: launch_pdl(a2_kernel, h_nsm, A2_THREADS, A2_SMEM, 0, h_tmO, h_tmR0, h_tmX1st); break;
        case 3: launch_pdl(conv_kernel, DM / CV_CPB, CV_THREADS, CV_SMEM, (const bf16*)d_in[9], 0, h_tmOut); break;
        case 5: launch_pdl(a1_kernel, h_nsm, A1_THREADS, A1_SMEM, 1, (const bf16*)d_in[0], h_tmX1, h_tmR1, h_tmOst); break;
        case 6: launch_pdl(a2_kernel, h_nsm, A2_THREADS, A2_SMEM, 1, h_tmO, h_tmR1, h_tmX1st); break;
        case 7: launch_pdl(conv_kernel, DM / CV_CPB, CV_THREADS, CV_SMEM, (const bf16*)d_in[9], 1, h_tmOut); break;
        default: break;
    }
}
static int n_stage_kernels() { return 9; }
static const char* stage_name(int k) { const char* n[] = {"kgen", "a1", "a2", "conv", "tr", "a1", "a2", "conv", "tr"}; return n[k]; }

extern "C" void kernel_launch(void* const* d_in, const int* in_sizes, int n_in, void* d_out, int out_size) {
    (void)in_sizes; (void)n_in; (void)out_size;
    static const void *p_in = nullptr, *p_out = nullptr;
    if (p_in != d_in[0] || p_out != d_out) {
        cudaFuncSetAttribute(conv_kernel, cudaFuncAttributeMaxDynamicSharedMemorySize, CV_SMEM);
        cudaFuncSetAttribute(kgen_kernel, cudaFuncAttributePreferredSharedMemoryCarveout, 100);
        cudaFuncSetAttribute(a1_kernel, cudaFuncAttributeMaxDynamicSharedMemorySize, A1_SMEM);
        cudaFuncSetAttribute(a2_kernel, cudaFuncAttributeMaxDynamicSharedMemorySize, A2_SMEM);
        int dev; cudaGetDevice(&dev); cudaDeviceGetAttribute(&h_nsm, cudaDevAttrMultiProcessorCount, dev);
        if (h_nsm != 132) h_nsm = 128;
        void *po, *px1, *px2;
        cudaGetSymbolAddress(&po, g_o); cudaGetSymbolAddress(&px1, g_x1T); cudaGetSymbolAddress(&px2, g_xcT);
        make_tmap(&h_tmO, po, 640, 2048, 64, 128, CU_TENSOR_MAP_SWIZZLE_128B);
        make_tmap(&h_tmOst, po, 640, 2048, 80, 16, CU_TENSOR_MAP_SWIZZLE_NONE);
        make_tmap(&h_tmX0, d_in[0], 640, 2048, 64, 128, CU_TENSOR_MAP_SWIZZLE_128B);
        make_tmap(&h_tmX1, px2, 2048, 640, 64, 64, CU_TENSOR_MAP_SWIZZLE_128B, XCP);
        make_tmap(&h_tmR0, d_in[0], 640, 2048, 80, 128, CU_TENSOR_MAP_SWIZZLE_NONE);
        make_tmap(&h_tmR1, px2, 2048, 640, 64, 80, CU_TENSOR_MAP_SWIZZLE_128B, XCP);
        make_tmap(&h_tmX1st, px1, 2048, 640, 64, 80, CU_TENSOR_MAP_SWIZZLE_128B, XCP);
        make_tmap(&h_tmOut, d_out, 640, 2048, 80, 8, CU_TENSOR_MAP_SWIZZLE_NONE);
        p_in = d_in[0]; p_out = d_out;
    }
    for (int k = 0; k < n_stage_kernels(); k++) launch_stage(k, d_in, d_out);
}
```

```cpp
#include <cuda_runtime.h>
#include <cuda_bf16.h>
#include <stdint.h>
#include <cuda.h>

typedef __nv_bfloat16 bf16;

constexpr int SEQ = 2048;
constexpr int DM = 640;
constexpr int NMODE = 192;

__device__ __forceinline__ float bf2f(bf16 v) { return __bfloat162float(v); }
__device__ __forceinline__ float rbf(float v) {
    uint32_t r;
    asm("cvt.rn.bf16x2.f32 %0, %1, %2;" : "=r"(r) : "f"(v), "f"(0.f));
    return __uint_as_float(r);
}
__device__ __forceinline__ uint32_t pack2(float lo, float hi) {
    __nv_bfloat162 t = __floats2bfloat162_rn(lo, hi);
    return *reinterpret_cast<uint32_t*>(&t);
}
__device__ __forceinline__ void pdl_sync() {
    asm volatile("griddepcontrol.wait;" ::: "memory");
    asm volatile("griddepcontrol.launch_dependents;" ::: "memory");
}
__device__ __forceinline__ float sqrt_apx(float v) { float r; asm("sqrt.approx.ftz.f32 %0, %1;" : "=f"(r) : "f"(v)); return r; }
__device__ __forceinline__ float rcp_apx(float v) { float r; asm("rcp.approx.ftz.f32 %0, %1;" : "=f"(r) : "f"(v)); return r; }
__device__ __forceinline__ uint32_t smem_u32(const void* p) { return (uint32_t)__cvta_generic_to_shared(p); }

constexpr int TPAD = 16;
constexpr int DLEN = 544;
constexpr int TAP_W2 = DLEN * 8, TAP_W3 = TAP_W2 + 768, TAP_C = TAP_W3 + 768, TAPB = TAP_C + 384;
__device__ __align__(128) uint4 g_tap[DM * 128];
#define XPAD 64
constexpr int XCP = SEQ + XPAD;
__device__ __align__(128) bf16 g_x1T[DM * XCP];
__device__ __align__(128) bf16 g_xcT[DM * XCP];
__device__ __align__(128) bf16 g_o[SEQ * DM];
constexpr int WQ_STAGE = 240 * 128, WO_STAGE = 80 * 128;
__device__ __align__(128) uint4 g_wq[8 * 10 * WQ_STAGE / 16];
__device__ __align__(128) uint4 g_wo[8 * 10 * WO_STAGE / 16];
__device__ __align__(16) float g_csp[10 * 1920];
__device__ __align__(16) float2 g_sum[2 * SEQ];
__device__ __align__(16) bf16 g_piv[2 * SEQ];
__device__ __align__(128) bf16 g_yT[DM * XCP];
__device__ uint32_t g_epoch;
__device__ __align__(16) unsigned long long g_rstat[SEQ];
__device__ ulonglong2 g_part[16 * 8 * 128];
__device__ ulonglong2 g_halo[2 * 16 * 8 * 640];
__device__ __forceinline__ unsigned long long tagw(uint32_t payload, uint32_t tag) { return ((unsigned long long)tag << 32) | payload; }
__device__ __forceinline__ void st_tag2(ulonglong2* p, uint32_t a, uint32_t b, uint32_t tag) {
    asm volatile("st.global.cg.v2.u64 [%0], {%1, %2};" ::"l"(p), "l"(tagw(a, tag)), "l"(tagw(b, tag)) : "memory");
}
__device__ __forceinline__ ulonglong2 ld_tag2(const ulonglong2* p) {
    ulonglong2 v;
    asm volatile("ld.relaxed.gpu.global.v2.u64 {%0, %1}, [%2];" : "=l"(v.x), "=l"(v.y) : "l"(p) : "memory");
    return v;
}
__device__ __forceinline__ bool tag_ok(ulonglong2 v, uint32_t tag) { return (uint32_t)(v.x >> 32) == tag && (uint32_t)(v.y >> 32) == tag; }
__device__ __forceinline__ uint32_t ld_epoch() { uint32_t v; asm volatile("ld.relaxed.gpu.global.u32 %0, [%1];" : "=r"(v) : "l"(&g_epoch) : "memory"); return v + 1; }
constexpr int SPIN_MAX = 1 << 20;
__device__ uint32_t g_started[4];
__device__ __forceinline__ void sm_started(int slot) { asm volatile("red.relaxed.gpu.global.add.u32 [%0], 1;" ::"l"(g_started + slot) : "memory"); }
__device__ __noinline__ void sm_idle(int slot) {
    if (threadIdx.x) return;
    sm_started(slot);
    const uint32_t want = ld_epoch() * gridDim.x;
    pdl_sync();
#pragma unroll 1
    for (int it = 0; it < SPIN_MAX; it++) {
        uint32_t v;
        asm volatile("ld.relaxed.gpu.global.u32 %0, [%1];" : "=r"(v) : "l"(g_started + slot) : "memory");
        if ((int)(v - want) >= 0) break;
        __nanosleep(100);
    }
}
__device__ __forceinline__ int sm_tile() {
    uint32_t s;
    asm volatile("mov.u32 %0, %smid;" : "=r"(s));
    const uint32_t h = (s - 64) >> 1, q = (h * 37) >> 8;
    const int t0 = ((s >> 1) & 7) * 16 + (s >> 4) * 2 + (s & 1), t1 = (1 + h - 7 * q) * 16 + 8 + q * 2 + (s & 1), t2 = s - 124 < 8 ? s - 116 : 128;
    return gridDim.x == 128 ? (int)blockIdx.x : s < 64 ? t0 : s < 120 ? t1 : t2;
}
#define DBG_SYMS
#define TSTAMP(i)
#define TSTAMP1(i)
#define TSTAMP1T(i, t)
#define TSTAMP1X(i, t)
#define SPAN(k, i)
#define GSTAMP(arr, i)
#define TSTAMP2(i)
#define TSTAMP3(i)
#define TSTAMP4(i)
#define TSTAMPK(i, t)

__device__ __forceinline__ float2 cexp_at(float wr2, float wi, float p) {
    float er;
    asm("ex2.approx.ftz.f32 %0, %1;" : "=f"(er) : "f"(wr2 * p));
    float th = wi * p;
    const float k = rintf(th * 0.15915494309189535f);
    th = fmaf(k, -6.2831854820251465f, th);
    th = fmaf(k, 1.7484555314695172e-7f, th);
    return make_float2(er * __cosf(th), er * __sinf(th));
}
__device__ __forceinline__ float2 cmul(float2 a, float2 b) {
    return make_float2(fmaf(a.x, b.x, -a.y * b.y), fmaf(a.x, b.y, a.y * b.x));
}
__device__ __forceinline__ float2 csqr(float2 a) { return make_float2(fmaf(a.x, a.x, -a.y * a.y), (a.x + a.x) * a.y); }
__device__ __forceinline__ uint32_t packh(float2 v) {
    uint32_t r;
    asm("cvt.rn.f16x2.f32 %0, %1, %2;" : "=r"(r) : "f"(v.y), "f"(v.x));
    return r;
}
__device__ __forceinline__ void mma_f16(float* d, uint32_t a0, uint32_t a1, uint32_t a2, uint32_t a3, uint32_t b0, uint32_t b1) {
    asm volatile("mma.sync.aligned.m16n8k16.row.col.f32.f16.f16.f32 {%0,%1,%2,%3}, {%4,%5,%6,%7}, {%8,%9}, {%0,%1,%2,%3};"
                 : "+f"(d[0]), "+f"(d[1]), "+f"(d[2]), "+f"(d[3]) : "r"(a0), "r"(a1), "r"(a2), "r"(a3), "r"(b0), "r"(b1));
}

struct KgIn { const bf16 *logA, *Aim, *Cre, *Cim, *logdt, *x, *wqkv, *wo; };
constexpr int KG_THREADS = NMODE / 2;

__global__ void __launch_bounds__(KG_THREADS, 5) kgen_kernel(const KgIn in) {
    __shared__ __align__(128) uint4 tab[3 * 896];
    __shared__ __align__(16) unsigned short E[1024];
    const int d = blockIdx.x, tid = threadIdx.x, lane = tid & 31, warp = tid >> 5;
    SPAN(0, 0); SPAN(0, 1);
    TSTAMPK(0, 0);
    asm volatile("griddepcontrol.launch_dependents;" ::: "memory");
    const bf16 pdt = in.logdt[d];
    const uint32_t pla = reinterpret_cast<const uint32_t*>(in.logA)[d * KG_THREADS + tid], pai = reinterpret_cast<const uint32_t*>(in.Aim)[d * KG_THREADS + tid];
    const uint32_t pcr = reinterpret_cast<const uint32_t*>(in.Cre)[d * KG_THREADS + tid], pci = reinterpret_cast<const uint32_t*>(in.Cim)[d * KG_THREADS + tid];
    const bf16* pfq = tid < 30 ? in.wqkv + (size_t)(d * 30 + tid) * 64 : tid < 40 ? in.wo + (size_t)(d * 10 + tid - 30) * 64 : in.x + (size_t)(d * 32 + tid - 40) * 64;
    if (tid < 72) asm volatile("prefetch.global.L2 [%0];" ::"l"(pfq));
    reinterpret_cast<uint4*>(E)[tid] = make_uint4(0, 0, 0, 0);
    if (tid < 32) reinterpret_cast<uint4*>(E)[96 + tid] = make_uint4(0, 0, 0, 0);
    const uint32_t tw = smem_u32(tab) + warp * 14336;
    const int g = lane >> 2, t = lane & 3;
    const uint32_t sta = tw + lane * 128 + ((2 * (lane & 3) + ((lane >> 2) & 1)) << 4);
    const uint32_t lda = tw + t * 128 + ((g ^ (2 * t)) << 4);
    const uint32_t stb = tw + 12288 + lane * 64 + ((4 * ((lane >> 1) & 1) + ((lane >> 2) & 3)) << 3);
    const uint32_t ldb = tw + 12288 + t * 64 + ((g ^ (4 * (t >> 1))) << 3);
    auto sts4 = [&](int e, int off, uint32_t a, uint32_t b, uint32_t c, uint32_t dd) {
        asm volatile("st.shared.v4.u32 [%0], {%1,%2,%3,%4};" ::"r"((sta ^ (e << 4)) + off), "r"(a), "r"(b), "r"(c), "r"(dd) : "memory");
    };
    auto lds4 = [&](int sp, int off, uint32_t* r) {
        asm volatile("ld.shared.v4.u32 {%0,%1,%2,%3}, [%4];" : "=r"(r[0]), "=r"(r[1]), "=r"(r[2]), "=r"(r[3]) : "r"((lda ^ ((sp & 1) << 4)) + sp * 512 + off) : "memory");
    };
    const float dt = rbf(expf(bf2f(pdt)));
    float2 C[2], y1[2], z8[2], y128[2];
    float cmax = 0.f;
#pragma unroll
    for (int m = 0; m < 2; m++) {
        const float wr2 = -rbf(expf(__uint_as_float(m ? pla & 0xffff0000u : pla << 16))) * dt * 1.4426950408889634f;
        const float wi = __uint_as_float(m ? pai & 0xffff0000u : pai << 16) * dt;
        C[m] = make_float2(__uint_as_float(m ? pcr & 0xffff0000u : pcr << 16) * dt, -__uint_as_float(m ? pci & 0xffff0000u : pci << 16) * dt);
        cmax = fmaxf(cmax, fmaxf(fabsf(C[m].x), fabsf(C[m].y)));
        y1[m] = cexp_at(wr2, -wi, 1.f); z8[m] = cexp_at(wr2, wi, 8.f); y128[m] = cexp_at(wr2, -wi, 128.f);
    }
    const int ex = min(max((int)(__reduce_max_sync(~0u, __float_as_uint(cmax)) >> 23), 20), 240);
    const float scale = __uint_as_float((uint32_t)(127 + 10 + 127 - ex) << 23), unscale = 2.0f * __uint_as_float((uint32_t)(ex - 10) << 23);
    TSTAMPK(4, 0);
    float k2048 = 0.f;
    {
        float2 h0[2], h1[2], g0[2], g1[2], g2[2], g2b[2], g3[2], g4[2], y2[2], y4[2];
#pragma unroll
        for (int m = 0; m < 2; m++) {
            h0[m] = make_float2(1.f, 0.f); h1[m] = csqr(csqr(csqr(z8[m])));
            g0[m] = make_float2(C[m].x * scale, C[m].y * scale);
            g1[m] = cmul(g0[m], y128[m]);
            const float2 y256 = csqr(y128[m]), y512 = csqr(y256);
            g2b[m] = g2[m] = cmul(g0[m], y256); g3[m] = cmul(g0[m], y512); g4[m] = cmul(g3[m], y512);
            y2[m] = csqr(y1[m]); y4[m] = csqr(y2[m]);
        }
#pragma unroll
        for (int e = 0; e < 8; e++) {
            sts4(e, 0, packh(h0[0]), packh(h1[0]), packh(h0[1]), packh(h1[1]));
            sts4(e, 4096, packh(g0[0]), packh(g0[1]), packh(g1[0]), packh(g1[1]));
            sts4(e, 8192, packh(g2[0]), packh(g2[1]), packh((e & 1) ? cmul(g3[0], y4[0]) : g3[0]), packh((e & 1) ? cmul(g3[1], y4[1]) : g3[1]));
            asm volatile("st.shared.v2.u32 [%0], {%1,%2};" ::"r"(stb ^ (e << 3)), "r"(packh(g4[0])), "r"(packh(g4[1])) : "memory");
#pragma unroll
            for (int m = 0; m < 2; m++) {
                if (e < 7) {
                    h0[m] = e ? cmul(h0[m], z8[m]) : z8[m]; h1[m] = cmul(h1[m], z8[m]); g0[m] = cmul(g0[m], y1[m]); g1[m] = cmul(g1[m], y1[m]);
                    g2[m] = e == 3 ? cmul(g2b[m], y128[m]) : cmul(g2[m], y2[m]);
                    if (e & 1) g3[m] = cmul(g3[m], y128[m]);
                    g4[m] = cmul(g4[m], y128[m]);
                } else k2048 += fmaf(g4[m].x, y128[m].x, -g4[m].y * y128[m].y);
            }
        }
    }
    TSTAMPK(6, 0);
    const int job = warp * DM + d;
    const bool isq = job < 1200;
    uint32_t sw[16];
    unsigned char* sdst = nullptr;
    int sn = 0;
    if (job < 1600) {
        const int j2 = isq ? job : job - 1200, kb = j2 % 10, col = (j2 / 10) * 16 + (lane >> 3) * 4;
        if (isq) {
            const int sec = col / DM, r = col - sec * DM, hg = r / 80;
            sn = hg * 160 + sec * 80 + r;
            sdst = reinterpret_cast<unsigned char*>(g_wq) + (hg * 9 + kb) * WQ_STAGE;
        } else {
            sn = col;
            sdst = reinterpret_cast<unsigned char*>(g_wo) + ((col / 80) * 9 + kb) * WO_STAGE;
        }
        const int pitch = isq ? 3 * DM : DM;
        const bf16* src = (isq ? in.wqkv : in.wo) + (size_t)(kb * 64 + (lane & 7) * 8) * pitch + col;
#pragma unroll
        for (int i = 0; i < 8; i++) {
            const uint2 v = __ldg(reinterpret_cast<const uint2*>(src + i * pitch));
            sw[2 * i] = v.x; sw[2 * i + 1] = v.y;
        }
        sn += kb << 16;
    } else if (job < 1600 + 64) {
        reinterpret_cast<uint4*>(g_sum)[(job - 1600) * 32 + lane] = make_uint4(0, 0, 0, 0);
    }
    __syncwarp();
    float acc[5][4];
#pragma unroll
    for (int j = 0; j < 5; j++)
#pragma unroll
        for (int k = 0; k < 4; k++) acc[j][k] = 0.f;
#pragma unroll
    for (int sp = 0; sp < 8; sp++) {
        uint32_t a[4], b[4], c[4], e0, e1;
        lds4(sp, 0, a); lds4(sp, 4096, b); lds4(sp, 8192, c);
        asm volatile("ld.shared.v2.u32 {%0,%1}, [%2];" : "=r"(e0), "=r"(e1) : "r"((ldb ^ ((sp & 3) << 3)) + sp * 256) : "memory");
        mma_f16(acc[0], a[0], a[1], a[2], a[3], b[0], b[1]);
        mma_f16(acc[1], a[0], a[1], a[2], a[3], b[2], b[3]);
        mma_f16(acc[2], a[0], a[1], a[2], a[3], c[0], c[1]);
        mma_f16(acc[3], a[0], a[1], a[2], a[3], c[2], c[3]);
        mma_f16(acc[4], a[0], a[1], a[2], a[3], e0, e1);
    }
#pragma unroll
    for (int o = 16; o; o >>= 1) k2048 += __shfl_xor_sync(~0u, k2048, o);
    __syncwarp();
    {
        float* Pp = reinterpret_cast<float*>(tab + warp * 896);
#pragma unroll
        for (int h = 0; h < 2; h++) {
            const int b = g + 8 * h;
            *reinterpret_cast<float2*>(Pp + 8 * b + 2 * t) = make_float2(acc[0][2 * h] * unscale, acc[0][2 * h + 1] * unscale);
            *reinterpret_cast<float2*>(Pp + 128 + 8 * b + 2 * t) = make_float2(acc[1][2 * h] * unscale, acc[1][2 * h + 1] * unscale);
            *reinterpret_cast<float2*>(Pp + 256 + 4 * b + 2 * (t & 1) + 64 * (t >> 1)) = make_float2(acc[2][2 * h] * unscale, acc[2][2 * h + 1] * unscale);
            *reinterpret_cast<float2*>(Pp + 384 + 2 * b + 32 * t) = make_float2(acc[3][2 * h] * unscale, acc[3][2 * h + 1] * unscale);
            Pp[512 + b + 32 * t] = acc[4][2 * h] * unscale;
            Pp[512 + b + 32 * t + 16] = acc[4][2 * h + 1] * unscale;
        }
        if (lane == 0) Pp[640] = k2048 * unscale;
    }
    TSTAMPK(7, 0);
    __syncthreads();
    TSTAMPK(9, 0);
    const float* Kp = reinterpret_cast<const float*>(tab);
    auto ksum = [&](int i) -> float { return (Kp[i] + Kp[3584 + i]) + Kp[7168 + i]; };
    auto ksum4 = [&](int q) -> float4 {
        const float4 a = reinterpret_cast<const float4*>(Kp)[q], b = reinterpret_cast<const float4*>(Kp)[896 + q], c = reinterpret_cast<const float4*>(Kp)[1792 + q];
        return make_float4((a.x + b.x) + c.x, (a.y + b.y) + c.y, (a.z + b.z) + c.z, (a.w + b.w) + c.w);
    };
    uint32_t* E2w = reinterpret_cast<uint32_t*>(E);
    {
        float4 v = ksum4(tid);
        if (tid == 95) v.w -= rbf(ksum(384));
        const uint32_t lo = pack2(v.x, v.y), hi = pack2(v.z, v.w);
        if (tid < 64) { E2w[9 + 2 * tid] = lo; E2w[10 + 2 * tid] = hi; }
        else {
            const int l = 256 + 8 * (tid - 64);
            if (tid > 64) E[18 + l - 1] = (unsigned short)lo;
            E2w[9 + l / 2] = __byte_perm(lo, 0, 0x1010);
            E2w[10 + l / 2] = __byte_perm(lo, hi, 0x5432);
            E2w[11 + l / 2] = __byte_perm(hi, 0, 0x1010);
            E[18 + l + 6] = (unsigned short)(hi >> 16);
        }
    }
    if (tid < 64) {
        float4 v = ksum4(96 + tid);
        if (tid == 31) v.w -= rbf(ksum(512));
        const int o = (tid < 32 ? 317 : 417 - 64) + 2 * tid;
        E2w[o] = pack2(v.x, v.y); E2w[o + 1] = pack2(v.z, v.w);
    } else if (tid == 88) E[800 + 34 + 128] = (unsigned short)(__float_as_uint(rbf(ksum(640))) >> 16);
    if (job < 1600) {
        const int c = lane & 7, n = sn & 0xffff;
#pragma unroll
        for (int q = 0; q < 4; q++) {
            uint32_t w[4];
#pragma unroll
            for (int j = 0; j < 4; j++) w[j] = __byte_perm(sw[4 * j + (q >> 1)], sw[4 * j + 2 + (q >> 1)], (q & 1) ? 0x7632 : 0x5410);
            *reinterpret_cast<uint4*>(sdst + (n + q) * 128 + ((c ^ ((n + q) & 7)) << 4)) = make_uint4(w[0], w[1], w[2], w[3]);
        }
    }
    __syncthreads();
    g_tap[d * 128 + tid] = reinterpret_cast<const uint4*>(E)[tid];
    if (tid < 32) g_tap[d * 128 + 96 + tid] = reinterpret_cast<const uint4*>(E)[96 + tid];
    TSTAMPK(10, 0);
    if (isq) {
        float4 a = make_float4(0.f, 0.f, 0.f, 0.f);
#pragma unroll
        for (int i = 0; i < 8; i++) {
            a.x += __uint_as_float(sw[2 * i] << 16); a.y += __uint_as_float(sw[2 * i] & 0xffff0000u);
            a.z += __uint_as_float(sw[2 * i + 1] << 16); a.w += __uint_as_float(sw[2 * i + 1] & 0xffff0000u);
        }
#pragma unroll
        for (int o = 1; o <= 4; o <<= 1) {
            a.x += __shfl_xor_sync(~0u, a.x, o); a.y += __shfl_xor_sync(~0u, a.y, o);
            a.z += __shfl_xor_sync(~0u, a.z, o); a.w += __shfl_xor_sync(~0u, a.w, o);
        }
        if ((lane & 7) == 0) *reinterpret_cast<float4*>(g_csp + (sn >> 16) * 1920 + (sn & 0xffff)) = a;
    }
    TSTAMPK(11, 0);
    SPAN(0, 3);
}

#define CV_MODE 0
#define CV_SLEEP 100
constexpr int CV_CPB = 5;
constexpr int CV_THREADS = 512;
constexpr int UPADF = 128;
constexpr int ULEN = UPADF + SEQ + 80;
constexpr int XLEN = SEQ + 16;
constexpr int BX_5 = 0, BX_3 = 3264, BX_9 = 6528, BX_7 = 8960, BX_LEN = 11392;
constexpr int CV_SM_T = 0;
constexpr int CV_SM_B = CV_CPB * TAPB;
constexpr int CV_SM_U = CV_SM_B + CV_CPB * BX_LEN;
constexpr int CV_SM_X = CV_SM_U + CV_CPB * ULEN * 2;
constexpr int CV_SM_Y = CV_SM_X + CV_CPB * XLEN * 2;
constexpr int CV_SM_P = CV_SM_Y + CV_CPB * XLEN * 2;
constexpr int CV_SM_CNT = CV_SM_P + 6 * 4096;
constexpr int CV_SM_O = (CV_SM_CNT + 128 + 127) & ~127;
constexpr int CV_SMEM = CV_SM_O + 20480;
static_assert(CV_SM_B % 128 == 0 && CV_SM_CNT % 16 == 0, "layout");

__device__ __forceinline__ void mma_bf16(float* d, uint32_t a0, uint32_t a1, uint32_t a2, uint32_t a3, uint32_t b0, uint32_t b1) {
    asm volatile("mma.sync.aligned.m16n8k16.row.col.f32.bf16.bf16.f32 {%0,%1,%2,%3}, {%4,%5,%6,%7}, {%8,%9}, {%0,%1,%2,%3};"
                 : "+f"(d[0]), "+f"(d[1]), "+f"(d[2]), "+f"(d[3]) : "r"(a0), "r"(a1), "r"(a2), "r"(a3), "r"(b0), "r"(b1));
}
__device__ __forceinline__ void mma_bf16_k8(float* d, uint32_t a0, uint32_t a1, uint32_t b0) {
    asm volatile("mma.sync.aligned.m16n8k8.row.col.f32.bf16.bf16.f32 {%0,%1,%2,%3}, {%4,%5}, {%6}, {%0,%1,%2,%3};"
                 : "+f"(d[0]), "+f"(d[1]), "+f"(d[2]), "+f"(d[3]) : "r"(a0), "r"(a1), "r"(b0));
}
__device__ __forceinline__ void ldsm_x4(uint32_t* r, uint32_t addr) {
    asm volatile("ldmatrix.sync.aligned.m8n8.x4.shared.b16 {%0,%1,%2,%3}, [%4];"
                 : "=r"(r[0]), "=r"(r[1]), "=r"(r[2]), "=r"(r[3]) : "r"(addr));
}

__device__ __forceinline__ void ldsm_x4_t(uint32_t* r, uint32_t addr) {
    asm volatile("ldmatrix.sync.aligned.m8n8.x4.trans.shared.b16 {%0,%1,%2,%3}, [%4];"
                 : "=r"(r[0]), "=r"(r[1]), "=r"(r[2]), "=r"(r[3]) : "r"(addr));
}
__device__ __forceinline__ uint32_t ln2(uint32_t x, uint32_t m, float ra, float rb) {
    const __nv_bfloat162 d = __hsub2(*reinterpret_cast<const __nv_bfloat162*>(&x), *reinterpret_cast<const __nv_bfloat162*>(&m));
    const uint32_t w = *reinterpret_cast<const uint32_t*>(&d);
    return pack2(__uint_as_float(w << 16) * ra, __uint_as_float(w & 0xffff0000u) * rb);
}
__device__ __forceinline__ void cp_async16(uint32_t dst, const void* src) {
    asm volatile("cp.async.cg.shared.global [%0], [%1], 16;" ::"r"(dst), "l"(src));
}
__device__ __forceinline__ void cp_async_wait_all() { asm volatile("cp.async.wait_all;" ::: "memory"); }

template <bool FULL>
__device__ __forceinline__ void direct_pass(float (&acc)[8][4], uint32_t ub, uint32_t o0, uint32_t o1, const uint2* __restrict__ Tp, bool first_half) {
    uint32_t sw[8][8];
#pragma unroll
    for (int j = 0; j < 8; j++) { ldsm_x4(&sw[j][0], ub + o0 + j * 256); ldsm_x4(&sw[j][4], ub + o1 + j * 256); }
#pragma unroll
    for (int M = 0; M < 4; M++) {
#pragma unroll
        for (int i = 0; i < 4; i++) {
            const uint2 hi = Tp[128 * M + 16 * i], lo = Tp[128 * M + 16 * i - 8];
#pragma unroll
            for (int j = FULL ? 0 : M; j < 8; j++) mma_bf16(acc[j], hi.x, hi.y, lo.x, lo.y, sw[(j - M) & 7][2 * i], sw[(j - M) & 7][2 * i + 1]);
        }
        if (FULL) {
            ldsm_x4(&sw[7 - M][0], ub + o0 - (M + 1) * 256);
            if (M < 3) ldsm_x4(&sw[7 - M][4], ub + o1 - (M + 1) * 256);
        }
    }
    if (first_half) {
        const uint2 hi = Tp[512], lo = Tp[504];
#pragma unroll
        for (int j = FULL ? 0 : 4; j < 8; j++) mma_bf16(acc[j], hi.x, hi.y, lo.x, lo.y, sw[(j - 4) & 7][0], sw[(j - 4) & 7][1]);
    }
}
__device__ __forceinline__ void mbar_init(uint32_t bar, int count) { asm volatile("mbarrier.init.shared::cta.b64 [%0], %1;" ::"r"(bar), "r"(count)); }
__device__ __forceinline__ void mbar_arrive(uint32_t bar) { asm volatile("mbarrier.arrive.shared::cta.b64 _, [%0];" ::"r"(bar) : "memory"); }
__device__ __forceinline__ void mbar_wait(uint32_t bar, uint32_t parity) {
    asm volatile("{\n.reg .pred p;\nWAIT_LOOP:\n"
                 "mbarrier.try_wait.parity.shared::cta.b64 p, [%0], %1;\n"
                 "@p bra.uni WAIT_DONE;\nbra.uni WAIT_LOOP;\nWAIT_DONE:\n}" ::"r"(bar), "r"(parity) : "memory");
}

__device__ __forceinline__ void mbar_expect_tx(uint32_t bar, uint32_t bytes) {
    asm volatile("mbarrier.arrive.expect_tx.shared::cta.b64 _, [%0], %1;" ::"r"(bar), "r"(bytes) : "memory");
}
__device__ __forceinline__ void tma_load_2d(uint32_t dst, const void* tmap, int c0, int c1, uint32_t bar) {
    asm volatile("cp.async.bulk.tensor.2d.shared::cluster.global.mbarrier::complete_tx::bytes [%0], [%1, {%3, %4}], [%2];"
                 ::"r"(dst), "l"(tmap), "r"(bar), "r"(c0), "r"(c1) : "memory");
}
__device__ __forceinline__ void fence_async_smem() { asm volatile("fence.proxy.async.shared::cta;" ::: "memory"); }
__device__ __forceinline__ void bulk_load(uint32_t dst, const void* src, uint32_t bytes, uint32_t bar) {
    asm volatile("cp.async.bulk.shared::cluster.global.mbarrier::complete_tx::bytes [%0], [%1], %2, [%3];"
                 ::"r"(dst), "l"(src), "r"(bytes), "r"(bar) : "memory");
}
__device__ __forceinline__ void tma_store_2d(const void* tmap, int c0, int c1, uint32_t src) {
    asm volatile("cp.async.bulk.tensor.2d.global.shared::cta.bulk_group [%0, {%1, %2}], [%3];" ::"l"(tmap), "r"(c0), "r"(c1), "r"(src) : "memory");
    asm volatile("cp.async.bulk.commit_group;" ::: "memory");
    asm volatile("cp.async.bulk.wait_group.read 0;" ::: "memory");
}
__device__ __forceinline__ void stsm_x4(uint32_t addr, uint32_t r0, uint32_t r1, uint32_t r2, uint32_t r3) {
    asm volatile("stmatrix.sync.aligned.m8n8.x4.shared.b16 [%0], {%1,%2,%3,%4};" ::"r"(addr), "r"(r0), "r"(r1), "r"(r2), "r"(r3) : "memory");
}
__device__ __forceinline__ void stsm_x4_t(uint32_t addr, uint32_t r0, uint32_t r1, uint32_t r2, uint32_t r3) {
    asm volatile("stmatrix.sync.aligned.m8n8.x4.trans.shared.b16 [%0], {%1,%2,%3,%4};" ::"r"(addr), "r"(r0), "r"(r1), "r"(r2), "r"(r3) : "memory");
}
__device__ __forceinline__ void prefetch_tmap(const void* tmap) { asm volatile("prefetch.tensormap [%0];" ::"l"(tmap) : "memory"); }

__device__ __forceinline__ uint32_t fin2(uint32_t x, uint32_t y, uint32_t u, uint32_t dk) {
    typedef __nv_bfloat162 b2;
    const b2 r = __hadd2_rn(*reinterpret_cast<const b2*>(&x), __hadd2_rn(*reinterpret_cast<const b2*>(&y),
                            __hmul2_rn(*reinterpret_cast<const b2*>(&u), *reinterpret_cast<const b2*>(&dk))));
    return *reinterpret_cast<const uint32_t*>(&r);
}
__global__ void __launch_bounds__(CV_THREADS, 1) conv_kernel(const bf16* __restrict__ Dskip, int layer, const __grid_constant__ CUtensorMap tmOut) {
    extern __shared__ __align__(128) unsigned char sm[];
    SPAN(3 + 4 * layer, 0);
    bf16* Us = reinterpret_cast<bf16*>(sm + CV_SM_U);
    bf16* Xs = reinterpret_cast<bf16*>(sm + CV_SM_X);
    bf16* Ys = reinterpret_cast<bf16*>(sm + CV_SM_Y);
    const int tid = threadIdx.x, lane = tid & 31, warp = __shfl_sync(~0u, tid >> 5, 0);
    const int d0 = blockIdx.x * CV_CPB, tile = blockIdx.x; (void)tile;
    TSTAMP1X(9, 256);
    unsigned short dskr;
    asm volatile("ld.global.nc.u16 %0, [%1];" : "=h"(dskr) : "l"(Dskip + d0 + min(lane, CV_CPB - 1)));
    if (tid >= 256) {
        const int t2 = tid - 256;
        if (t2 == 0) {
            mbar_init(smem_u32(sm + CV_SM_CNT) + 104, 1);
            asm volatile("fence.mbarrier_init.release.cluster;" ::: "memory");
            mbar_expect_tx(smem_u32(sm + CV_SM_CNT) + 104, CV_CPB * 2048);
            bulk_load(smem_u32(sm + CV_SM_O), g_tap + d0 * 128, CV_CPB * 2048, smem_u32(sm + CV_SM_CNT) + 104);
        } else if (lane == 0) {
            mbar_init(smem_u32(sm + CV_SM_CNT) + 16 * (warp - 9), warp == 15 ? 16 : 1);
            if (warp < 15) mbar_init(smem_u32(sm + CV_SM_CNT) + 16 * (warp - 9) + 8, 1);
            else if (layer) prefetch_tmap(&tmOut);
        }
        if (t2 < 149) {
            const int k = t2;
            const int off = k < 18 ? BX_5 + 8 * k : k < 37 ? BX_3 + 8 * (k - 18) : k < 69 ? BX_9 + 8 * (k - 37) : k < 101 ? BX_7 + 8 * (k - 69)
                          : k < 133 ? 8 * (k - 101) : (UPADF + SEQ) * 2 + 8 * (k - 133);
#pragma unroll
            for (int c = 0; c < CV_CPB; c++) *reinterpret_cast<uint2*>(sm + (k < 101 ? CV_SM_B + c * BX_LEN : CV_SM_U + c * ULEN * 2) + off) = make_uint2(0, 0);
        }
        asm volatile("bar.sync 1, 256;" ::: "memory");
        TSTAMP1X(10, 256);
        mbar_wait(smem_u32(sm + CV_SM_CNT) + 104, 0);
        TSTAMP1X(11, 256);
#pragma unroll 1
        for (int r = t2; r < 392; r += 256) {
            const bool dd = r < 272, cc = r >= 368;
            const uint32_t* E2 = reinterpret_cast<const uint32_t*>(sm + CV_SM_O) + (dd ? r : r < 320 ? 300 + 2 * (r - 272) : cc ? 416 : 400 + 2 * (r - 320));
            const uint32_t* E3 = E2 + (dd ? 4 : cc ? 0 : 1);
            const uint32_t s0 = !cc ? 0x7610u : r == 382 ? 0x1044u : 0x4444u, s1 = !cc ? 0x7610u : r == 378 ? 0x1044u : 0x4444u;
            const uint32_t s2 = !cc ? 0x1032u : r == 381 ? 0x4410u : 0x4444u, s3 = !cc ? 0x1032u : r == 377 ? 0x4410u : 0x4444u;
            uint32_t w[CV_CPB][4];
#pragma unroll
            for (int c = 0; c < CV_CPB; c++) { w[c][0] = E2[512 * c]; w[c][1] = E2[512 * c + 1]; w[c][2] = E3[512 * c]; w[c][3] = E3[512 * c + 1]; }
#pragma unroll
            for (int c = 0; c < CV_CPB; c++) {
                const uint32_t a = __byte_perm(w[c][3], w[c][2], s1), b = __byte_perm(w[c][1], w[c][0], s2);
                *reinterpret_cast<uint4*>(sm + CV_SM_T + c * TAPB + r * 16) =
                    make_uint4(__byte_perm(w[c][1], w[c][0], s0), dd || cc ? a : b, dd || cc ? b : a, __byte_perm(w[c][3], w[c][2], s3));
            }
        }
        TSTAMP1X(12, 256);
        if (layer == 0) {
#pragma unroll
            for (int c = 0; c < CV_CPB; c++) reinterpret_cast<uint4*>(g_yT + (size_t)(d0 + c) * XCP)[t2] = make_uint4(~0u, ~0u, ~0u, ~0u);
        }
        pdl_sync();
        if (layer && blockIdx.x == 0 && t2 == 0) g_epoch = ld_epoch();
    } else {
        const uint4* ppv = reinterpret_cast<const uint4*>(g_piv + layer * SEQ) + tid;
        const float4* psv = reinterpret_cast<const float4*>(g_sum + layer * SEQ) + tid;
        const uint4* pxv = reinterpret_cast<const uint4*>(g_x1T + (size_t)d0 * XCP) + tid;
        asm volatile("" : "+l"(ppv), "+l"(psv), "+l"(pxv));
        pdl_sync();
        SPAN(3 + 4 * layer, 1);
        TSTAMP(0);
        if (threadIdx.x == 0) { GSTAMP(g_tim, 15); }
        float4 sv[4];
#pragma unroll
        for (int k = 0; k < 4; k++) sv[k] = __ldcg(psv + 256 * k);
        const uint4 pv = __ldcg(ppv);
        uint4 xv[CV_CPB];
#pragma unroll
        for (int c = 0; c < CV_CPB; c++) xv[c] = __ldcg(pxv + c * (XCP / 8));
        uint32_t mw[4];
        float rs[8];
#pragma unroll
        for (int k = 0; k < 4; k++) {
            const uint32_t pw = k == 0 ? pv.x : k == 1 ? pv.y : k == 2 ? pv.z : pv.w;
            const float d0_ = sv[k].x * (1.0f / DM), d1_ = sv[k].z * (1.0f / DM);
            mw[k] = pack2(__uint_as_float(pw << 16) + d0_, __uint_as_float(pw & 0xffff0000u) + d1_);
            const uint32_t vr = pack2(fmaxf(fmaf(-d0_, d0_, sv[k].y * (1.0f / DM)), 0.f), fmaxf(fmaf(-d1_, d1_, sv[k].w * (1.0f / DM)), 0.f));
            const uint32_t ve = pack2(__uint_as_float(vr << 16) + 1e-5f, __uint_as_float(vr & 0xffff0000u) + 1e-5f);
            const uint32_t sd = pack2(sqrt_apx(__uint_as_float(ve << 16)), sqrt_apx(__uint_as_float(ve & 0xffff0000u)));
            rs[2 * k] = rcp_apx(__uint_as_float(sd << 16)); rs[2 * k + 1] = rcp_apx(__uint_as_float(sd & 0xffff0000u));
        }
        if (rs[0] != 123.f) TSTAMP(13);
        const int ch = tid + UPADF / 8, pch = ch ^ ((ch >> 3) & 1);
#pragma unroll
        for (int c = 0; c < CV_CPB; c++) {
            *reinterpret_cast<uint4*>(Xs + c * XLEN + tid * 8) = xv[c];
            *reinterpret_cast<uint4*>(Us + c * ULEN + pch * 8) =
                make_uint4(ln2(xv[c].x, mw[0], rs[0], rs[1]), ln2(xv[c].y, mw[1], rs[2], rs[3]), ln2(xv[c].z, mw[2], rs[4], rs[5]), ln2(xv[c].w, mw[3], rs[6], rs[7]));
        }
    }
    __syncthreads();
    TSTAMP(1);
    const uint32_t rstart = warp < 8 ? (warp < 4 ? 0x02000000u : 0x06040000u) : (warp < 12 ? 0x0C0B0A08u : 0x1E1D150Fu);
    const uint32_t rcount = warp < 8 ? 0x02020000u : (warp < 12 ? 0x03010102u : 0x01010806u);
#pragma unroll 1
    for (int rd = (rstart >> (8 * (warp & 3))) & 0xff, re = rd + ((rcount >> (8 * (warp & 3))) & 0xff); rd < re; rd++) {
        const int i = 32 * rd + lane;
        if (i < CV_CPB * 193) {
            const int c = i / 193, chunk = i - c * 193 - 1, ch = chunk + UPADF / 8;
            const bf16* uc = Us + c * ULEN;
            const uint4 o = *reinterpret_cast<const uint4*>(uc + (ch ^ ((ch >> 3) & 1)) * 8);
            const uint2 lo = *reinterpret_cast<const uint2*>(uc + ((ch - 1) ^ (((ch - 1) >> 3) & 1)) * 8 + 4);
            const uint2 hi = *reinterpret_cast<const uint2*>(uc + ((ch + 1) ^ (((ch + 1) >> 3) & 1)) * 8);
            const uint32_t w[8] = {lo.x, lo.y, o.x, o.y, o.z, o.w, hi.x, hi.y};
            float v[16], b[8];
#pragma unroll
            for (int k = 0; k < 8; k++) { v[2 * k] = __uint_as_float(w[k] << 16); v[2 * k + 1] = __uint_as_float(w[k] & 0xffff0000u); }
            unsigned char* bx = sm + CV_SM_B + c * BX_LEN + chunk * 16;
#pragma unroll
            for (int k = 0; k < 8; k++) b[k] = v[k + 4] + (v[k + 3] + v[k + 5]);
            *reinterpret_cast<uint2*>(bx + BX_3 + 168) = make_uint2(pack2(b[0], b[1]), pack2(b[2], b[3]));
            *reinterpret_cast<uint2*>(bx + BX_3 + 176) = make_uint2(pack2(b[4], b[5]), pack2(b[6], b[7]));
#pragma unroll
            for (int k = 0; k < 8; k++) b[k] += v[k + 2] + v[k + 6];
            *reinterpret_cast<uint4*>(bx + BX_5 + 160) = make_uint4(pack2(b[0], b[1]), pack2(b[2], b[3]), pack2(b[4], b[5]), pack2(b[6], b[7]));
            if (chunk < 128) {
#pragma unroll
                for (int k = 0; k < 8; k++) b[k] += v[k + 1] + v[k + 7];
                *reinterpret_cast<uint4*>(bx + BX_7 + 272) = make_uint4(pack2(b[0], b[1]), pack2(b[2], b[3]), pack2(b[4], b[5]), pack2(b[6], b[7]));
#pragma unroll
                for (int k = 0; k < 8; k++) b[k] += v[k] + v[k + 8];
                *reinterpret_cast<uint4*>(bx + BX_9 + 272) = make_uint4(pack2(b[0], b[1]), pack2(b[2], b[3]), pack2(b[4], b[5]), pack2(b[6], b[7]));
            }
        }
    }
    __syncwarp();
    if (lane == 0) mbar_arrive(smem_u32(sm + CV_SM_CNT) + 96);
    TSTAMP(2);
    {
        const int g = lane >> 2, ti = lane & 3;
        const int e = g - 2 * ti;
        uint32_t lds_off[4];
        uint32_t off2, off3, offc;
        {
            const int mat = lane >> 3, r = lane & 7;
#pragma unroll
            for (int pr = 0; pr < 4; pr++) {
                const int iw = 2 * pr + (mat >> 1), half = mat & 1;
                const int chunk = (UPADF - 16 * iw + 16 * r + 8 * half) >> 3;
                lds_off[pr] = (uint32_t)((chunk ^ ((chunk >> 3) & 1)) * 16);
            }
            const int j2 = 13 + r + 8 * (mat >> 1), j3 = j2 + 2, i0 = 8 * (mat & 1);
            off2 = (j2 & 1) ? BX_3 + (4 * j2 + i0 + 84) * 2 : BX_5 + (4 * j2 + i0 + 80) * 2;
            off3 = ((j3 & 1) ? BX_7 : BX_9) + (8 * j3 + i0 + 136) * 2;
            const int cc = (UPADF + 16 * (r + (mat >> 1)) + i0) >> 3;
            offc = (uint32_t)((cc ^ ((cc >> 3) & 1)) * 16);
        }
        const uint32_t rtab = warp < 8 ? (warp < 4 ? 0x0B090200u : 0x0C0A0301u) : (warp < 12 ? 0x13111008u : 0x1412241Cu);
        const int rl = (rtab >> (8 * (warp & 3))) & 0xff, type = rl >> 3, c = rl & 7;
        const int H = (type == 1 || type == 2) ? 1 : 0, T0 = 8 * H;
        const uint2* Tc = reinterpret_cast<const uint2*>(sm + CV_SM_T + c * TAPB) + TPAD + e;
        const uint32_t ubase = smem_u32(Us + c * ULEN);
        const uint32_t bbase = smem_u32(sm + CV_SM_B + c * BX_LEN);
        float acc[8][4];
#pragma unroll
        for (int j = 0; j < 8; j++)
#pragma unroll
            for (int k = 0; k < 4; k++) acc[j][k] = 0.f;
#pragma unroll 1
        for (int pass = (type == 2 || type == 4) ? 1 : 0; pass < ((type == 1 || type == 3) ? 1 : 2); pass++) {
            const uint32_t o0 = pass ? lds_off[2] : lds_off[0], o1 = pass ? lds_off[3] : lds_off[1];
            if (H) direct_pass<true>(acc, ubase + T0 * 256, o0, o1, Tc + 64 * pass, pass == 0);
            else direct_pass<false>(acc, ubase, o0, o1, Tc + 64 * pass, pass == 0);
        }
        TSTAMP(6);
        mbar_wait(smem_u32(sm + CV_SM_CNT) + 96, 0);
        if (type != 1 && type != 4) {
            const uint32_t* w2 = reinterpret_cast<const uint32_t*>(sm + CV_SM_T + c * TAPB + TAP_W2) + (115 - 96) + 4 * g - 2 * ti;
            uint32_t f[10][2];
#pragma unroll
            for (int k = 0; k < 10; k++) { f[k][0] = w2[16 * k]; f[k][1] = w2[16 * k - 8]; }
            const uint32_t ab = bbase + off2 + (2 * T0 + 6) * 128;
            const int kmax = H ? 23 : 8;
            uint32_t a[3][4];
            ldsm_x4_t(a[0], ab);
            ldsm_x4_t(a[1], ab - 128);
#pragma unroll
            for (int kp = 0; kp < 24; kp++) {
                if (kp > kmax) break;
                if (kp < 22) ldsm_x4_t(a[(kp + 2) % 3], ab - min(kp + 2, kmax) * 128);
#pragma unroll
                for (int j = 0; j < 8; j++) {
                    const int ee = 2 * j - 14 + kp;
                    if (ee >= 0 && ee <= 9) mma_bf16(acc[j], a[kp % 3][0], a[kp % 3][1], a[kp % 3][2], a[kp % 3][3], f[ee][0], f[ee][1]);
                }
            }
        }
        TSTAMP(7);
        if (type != 2 && type != 4) {
            const uint32_t* w3 = reinterpret_cast<const uint32_t*>(sm + CV_SM_T + c * TAPB + TAP_W3) + (129 - 96) + 2 * (g - ti);
            uint32_t f[9][2];
#pragma unroll
            for (int k = 0; k < 9; k++) { f[k][0] = w3[16 * k]; f[k][1] = w3[16 * k - 8]; }
            const uint32_t ab = bbase + off3 + (T0 - 2) * 256;
            uint32_t a[3][4];
            ldsm_x4_t(a[0], ab);
            ldsm_x4_t(a[1], ab - H * 256);
#pragma unroll
            for (int kp = 0; kp < 9; kp++) {
                if (kp > T0) break;
                if (kp < 7) ldsm_x4_t(a[(kp + 2) % 3], ab - min(kp + 2, T0) * 256);
#pragma unroll
                for (int j = 0; j < 8; j++) {
                    const int dl = j - 7 + kp;
                    if (dl >= 0 && dl <= 8) mma_bf16(acc[j], a[kp % 3][0], a[kp % 3][1], a[kp % 3][2], a[kp % 3][3], f[dl][0], f[dl][1]);
                }
            }
            const uint2* Dc = reinterpret_cast<const uint2*>(sm + CV_SM_T + c * TAPB + TAP_C) + e;
            const uint2 h63 = Dc[16], h64 = Dc[32], l63 = Dc[8], l64 = Dc[24];
#pragma unroll
            for (int j = 0; j < 8; j++)
                if (j == 7 || H) {
                    uint32_t bq[4];
                    ldsm_x4(bq, ubase + offc + (T0 + j - 8) * 256);
                    mma_bf16(acc[j], h64.x, h64.y, l64.x, l64.y, bq[0], bq[1]);
                    mma_bf16(acc[j], h63.x, h63.y, l63.x, l63.y, bq[2], bq[3]);
                }
        }
        TSTAMP(8);
        const bool hi_half = (type == 2 || type == 4);
        if (type != 0) {
            const int pair = H ? c : 5;
            float4* give = reinterpret_cast<float4*>(sm + CV_SM_P + pair * 4096 + (hi_half ? 2048 : 0)) + lane;
            const float4* take = reinterpret_cast<const float4*>(sm + CV_SM_P + pair * 4096 + (hi_half ? 0 : 2048)) + lane;
            const uint32_t pb = smem_u32(sm + CV_SM_CNT) + pair * 16;
#pragma unroll
            for (int j = 0; j < 4; j++)
                give[32 * j] = hi_half ? make_float4(acc[j][0], acc[j][1], acc[j][2], acc[j][3]) : make_float4(acc[j + 4][0], acc[j + 4][1], acc[j + 4][2], acc[j + 4][3]);
            __syncwarp();
            if (lane == 0) mbar_arrive(pb + (hi_half ? 8 : 0));
            mbar_wait(pb + (hi_half ? 0 : 8), 0);
#pragma unroll
            for (int j = 0; j < 4; j++) {
                const float4 v = take[32 * j];
                acc[j][0] = (hi_half ? acc[j + 4][0] : acc[j][0]) + v.x; acc[j][1] = (hi_half ? acc[j + 4][1] : acc[j][1]) + v.y;
                acc[j][2] = (hi_half ? acc[j + 4][2] : acc[j][2]) + v.z; acc[j][3] = (hi_half ? acc[j + 4][3] : acc[j][3]) + v.w;
            }
        }
        const uint32_t dk = __shfl_sync(~0u, (uint32_t)dskr, c) * 0x10001u;
#pragma unroll 1
        for (int rnd = 0; rnd < (type == 0 ? 2 : 1); rnd++) {
            const int Q = 2 * H + (hi_half ? 1 : rnd);
            if (rnd) {
#pragma unroll
                for (int j = 0; j < 4; j++)
#pragma unroll
                    for (int k = 0; k < 4; k++) acc[j][k] = acc[j + 4][k];
            }
            const uint32_t ya = smem_u32(Ys + c * XLEN) + (128 * (4 * Q + (lane >> 4)) + 16 * (lane & 7) + 8 * ((lane >> 3) & 1)) * 2;
#pragma unroll
            for (int j = 0; j < 4; j += 2)
                asm volatile("stmatrix.sync.aligned.m8n8.x4.trans.shared.b16 [%0], {%1,%2,%3,%4};" ::"r"(ya + j * 256),
                             "r"(pack2(acc[j][0], acc[j][1])), "r"(pack2(acc[j][2], acc[j][3])),
                             "r"(pack2(acc[j + 1][0], acc[j + 1][1])), "r"(pack2(acc[j + 1][2], acc[j + 1][3])) : "memory");
            __syncwarp();
            uint4 yv[2], xv[2], uv[2];
#pragma unroll
            for (int k = 0; k < 2; k++) {
                const int t = 512 * Q + 256 * k + 8 * lane, cu = (t + UPADF) >> 3;
                yv[k] = *reinterpret_cast<const uint4*>(Ys + c * XLEN + t);
                xv[k] = *reinterpret_cast<const uint4*>(Xs + c * XLEN + t);
                uv[k] = *reinterpret_cast<const uint4*>(Us + c * ULEN + (cu ^ ((cu >> 3) & 1)) * 8);
            }
#pragma unroll
            for (int k = 0; k < 2; k++)
                asm volatile("st.relaxed.gpu.global.v4.u32 [%0], {%1,%2,%3,%4};" ::"l"((layer ? g_yT : g_xcT) + (size_t)(d0 + c) * XCP + 512 * Q + 256 * k + 8 * lane),
                             "r"(fin2(xv[k].x, yv[k].x, uv[k].x, dk)), "r"(fin2(xv[k].y, yv[k].y, uv[k].y, dk)), "r"(fin2(xv[k].z, yv[k].z, uv[k].z, dk)), "r"(fin2(xv[k].w, yv[k].w, uv[k].w, dk)) : "memory");
        }
        TSTAMP(4);
        if (layer == 1) {
            const int mb = blockIdx.x >> 3, cg = blockIdx.x & 7;
            const bf16* src = g_yT + (size_t)(cg * 80 + (tid >> 4)) * XCP + mb * 128 + (tid & 15) * 8;
            uint32_t v[3][4];
            __syncthreads();
            TSTAMP(5);
            uint32_t todo = warp < 8 ? 7 : 3;
#pragma unroll 1
            for (int it = 0; it < SPIN_MAX; it++) {
#pragma unroll
                for (int k = 0; k < 3; k++)
                    if (todo >> k & 1)
                        asm volatile("ld.relaxed.gpu.global.v4.u32 {%0,%1,%2,%3}, [%4];" : "=r"(v[k][0]), "=r"(v[k][1]), "=r"(v[k][2]), "=r"(v[k][3]) : "l"(src + k * (32 * XCP)) : "memory");
#pragma unroll
                for (int k = 0; k < 3; k++)
                    if ((todo >> k & 1) && v[k][0] != ~0u && v[k][1] != ~0u && v[k][2] != ~0u && v[k][3] != ~0u) {
                        *reinterpret_cast<uint4*>(sm + (32 * k + (tid >> 4)) * 272 + (tid & 15) * 16) = make_uint4(v[k][0], v[k][1], v[k][2], v[k][3]);
                        todo ^= 1u << k;
                    }
                if (!todo) break;
                __nanosleep(CV_SLEEP);
            }
            __syncthreads();
            uint32_t w[12];
#pragma unroll
            for (int k = 0; k < 3; k++) ldsm_x4(&w[4 * k], smem_u32(sm) + min(32 * k + lane, 79) * 272 + warp * 16);
            const uint32_t ot = smem_u32(sm + CV_SM_O) + warp * 1280, oa = ot + (lane & 7) * 160 + (lane >> 3) * 16;
            stsm_x4_t(oa, w[0], w[1], w[2], w[3]);
            stsm_x4_t(oa + 64, w[4], w[5], w[6], w[7]);
            asm volatile("stmatrix.sync.aligned.m8n8.x2.trans.shared.b16 [%0], {%1,%2};" ::"r"(oa + 128), "r"(w[8]), "r"(w[9]) : "memory");
            fence_async_smem();
            __syncwarp();
            if (lane == 0) tma_store_2d(&tmOut, cg * 80, mb * 128 + 8 * warp, ot);
        }
    }
    TSTAMP(3);
    GSTAMP(g_tim, 14);
    SPAN(3 + 4 * layer, 3);
}

__device__ __forceinline__ void wgmma_fence() { asm volatile("wgmma.fence.sync.aligned;" ::: "memory"); }
__device__ __forceinline__ void wgmma_commit() { asm volatile("wgmma.commit_group.sync.aligned;" ::: "memory"); }
template <int N> __device__ __forceinline__ void wgmma_wait() { asm volatile("wgmma.wait_group.sync.aligned %0;" ::"n"(N) : "memory"); }
__device__ __forceinline__ uint64_t make_desc(uint32_t addr, uint32_t lbo, uint32_t sbo, uint32_t mode) {
    return (uint64_t)((addr & 0x3FFFF) >> 4) | ((uint64_t)(lbo >> 4) << 16) | ((uint64_t)(sbo >> 4) << 32) | ((uint64_t)mode << 62);
}
template <int TA, int TB>
__device__ __forceinline__ void wgmma_n240(float (&d)[120], uint64_t da, uint64_t db) {
    asm volatile("wgmma.mma_async.sync.aligned.m64n240k16.f32.bf16.bf16 {%0,%1,%2,%3,%4,%5,%6,%7,%8,%9,%10,%11,%12,%13,%14,%15,%16,%17,%18,%19,%20,%21,%22,%23,%24,%25,%26,%27,%28,%29,%30,%31,%32,%33,%34,%35,%36,%37,%38,%39,%40,%41,%42,%43,%44,%45,%46,%47,%48,%49,%50,%51,%52,%53,%54,%55,%56,%57,%58,%59,%60,%61,%62,%63,%64,%65,%66,%67,%68,%69,%70,%71,%72,%73,%74,%75,%76,%77,%78,%79,%80,%81,%82,%83,%84,%85,%86,%87,%88,%89,%90,%91,%92,%93,%94,%95,%96,%97,%98,%99,%100,%101,%102,%103,%104,%105,%106,%107,%108,%109,%110,%111,%112,%113,%114,%115,%116,%117,%118,%119}, %120, %121, 1, 1, 1, %122, %123;"
                 : "+f"(d[0]), "+f"(d[1]), "+f"(d[2]), "+f"(d[3]), "+f"(d[4]), "+f"(d[5]), "+f"(d[6]), "+f"(d[7]), "+f"(d[8]), "+f"(d[9]), "+f"(d[10]), "+f"(d[11]), "+f"(d[12]), "+f"(d[13]), "+f"(d[14]), "+f"(d[15]), "+f"(d[16]), "+f"(d[17]), "+f"(d[18]), "+f"(d[19]), "+f"(d[20]), "+f"(d[21]), "+f"(d[22]), "+f"(d[23]), "+f"(d[24]), "+f"(d[25]), "+f"(d[26]), "+f"(d[27]), "+f"(d[28]), "+f"(d[29]), "+f"(d[30]), "+f"(d[31]), "+f"(d[32]), "+f"(d[33]), "+f"(d[34]), "+f"(d[35]), "+f"(d[36]), "+f"(d[37]), "+f"(d[38]), "+f"(d[39]), "+f"(d[40]), "+f"(d[41]), "+f"(d[42]), "+f"(d[43]), "+f"(d[44]), "+f"(d[45]), "+f"(d[46]), "+f"(d[47]), "+f"(d[48]), "+f"(d[49]), "+f"(d[50]), "+f"(d[51]), "+f"(d[52]), "+f"(d[53]), "+f"(d[54]), "+f"(d[55]), "+f"(d[56]), "+f"(d[57]), "+f"(d[58]), "+f"(d[59]), "+f"(d[60]), "+f"(d[61]), "+f"(d[62]), "+f"(d[63]), "+f"(d[64]), "+f"(d[65]), "+f"(d[66]), "+f"(d[67]), "+f"(d[68]), "+f"(d[69]), "+f"(d[70]), "+f"(d[71]), "+f"(d[72]), "+f"(d[73]), "+f"(d[74]), "+f"(d[75]), "+f"(d[76]), "+f"(d[77]), "+f"(d[78]), "+f"(d[79]), "+f"(d[80]), "+f"(d[81]), "+f"(d[82]), "+f"(d[83]), "+f"(d[84]), "+f"(d[85]), "+f"(d[86]), "+f"(d[87]), "+f"(d[88]), "+f"(d[89]), "+f"(d[90]), "+f"(d[91]), "+f"(d[92]), "+f"(d[93]), "+f"(d[94]), "+f"(d[95]), "+f"(d[96]), "+f"(d[97]), "+f"(d[98]), "+f"(d[99]), "+f"(d[100]), "+f"(d[101]), "+f"(d[102]), "+f"(d[103]), "+f"(d[104]), "+f"(d[105]), "+f"(d[106]), "+f"(d[107]), "+f"(d[108]), "+f"(d[109]), "+f"(d[110]), "+f"(d[111]), "+f"(d[112]), "+f"(d[113]), "+f"(d[114]), "+f"(d[115]), "+f"(d[116]), "+f"(d[117]), "+f"(d[118]), "+f"(d[119])
                 : "l"(da), "l"(db), "n"(TA), "n"(TB));
}

template <int TA, int TB>
__device__ __forceinline__ void wgmma_n80(float (&d)[40], uint64_t da, uint64_t db) {
    asm volatile("wgmma.mma_async.sync.aligned.m64n80k16.f32.bf16.bf16 {%0,%1,%2,%3,%4,%5,%6,%7,%8,%9,%10,%11,%12,%13,%14,%15,%16,%17,%18,%19,%20,%21,%22,%23,%24,%25,%26,%27,%28,%29,%30,%31,%32,%33,%34,%35,%36,%37,%38,%39}, %40, %41, 1, 1, 1, %42, %43;"
                 : "+f"(d[0]), "+f"(d[1]), "+f"(d[2]), "+f"(d[3]), "+f"(d[4]), "+f"(d[5]), "+f"(d[6]), "+f"(d[7]), "+f"(d[8]), "+f"(d[9]), "+f"(d[10]), "+f"(d[11]), "+f"(d[12]), "+f"(d[13]), "+f"(d[14]), "+f"(d[15]), "+f"(d[16]), "+f"(d[17]), "+f"(d[18]), "+f"(d[19]), "+f"(d[20]), "+f"(d[21]), "+f"(d[22]), "+f"(d[23]), "+f"(d[24]), "+f"(d[25]), "+f"(d[26]), "+f"(d[27]), "+f"(d[28]), "+f"(d[29]), "+f"(d[30]), "+f"(d[31]), "+f"(d[32]), "+f"(d[33]), "+f"(d[34]), "+f"(d[35]), "+f"(d[36]), "+f"(d[37]), "+f"(d[38]), "+f"(d[39])
                 : "l"(da), "l"(db), "n"(TA), "n"(TB));
}

constexpr int A1_THREADS = 384;
constexpr int A1_NST = 4;
#define A1_PRE0 2
#define A1_SDELAY 1
#define A1_PRE1 1
constexpr int A1_STAGE = 16384 + WQ_STAGE;
constexpr int A1_KVP = 336;
constexpr int A1_SM_KV = 2 * A1_STAGE;
constexpr int A1_SM_O = A1_SM_KV + 144 * A1_KVP;
constexpr int A1_SM_R = A1_NST * A1_STAGE;
constexpr int A1_SM_BAR = A1_SM_R + 20480;
constexpr int A1_SM_CS = A1_SM_BAR + 256;
constexpr int A1_SM_RS = A1_SM_CS + 1024;
constexpr int A1_SM_RED = A1_SM_RS + 1024;
constexpr int A1_SMEM = A1_SM_RED + 1152 + 1024;
static_assert(A1_SM_O % 128 == 0 && A1_SM_O + 20480 <= A1_SM_R, "layout");

template <int L>
__device__ __forceinline__ void a1_mainloop(float (&acc)[120], uint32_t sbase, uint32_t bars, int wg, int tile) {
    constexpr int layer = L; (void)layer;
    const uint64_t da0 = L ? make_desc(sbase + wg * 8192, 8192, 1024, 1) : make_desc(sbase + wg * 8192, 16, 1024, 1), db0 = make_desc(sbase + 16384, 16, 1024, 1);
#pragma unroll 1
    for (int t = 0; t < 10; t++) {
        const int st = t % A1_NST;
        mbar_wait(bars + 8 * st, (t / A1_NST) & 1);
        TSTAMP3(1 + t);
        wgmma_fence();
#pragma unroll
        for (int kk = 0; kk < 4; kk++) wgmma_n240<L, 0>(acc, da0 + (uint32_t)(st * (A1_STAGE / 16) + kk * (L ? 128 : 2)), db0 + (uint32_t)(st * (A1_STAGE / 16) + kk * 2));
        wgmma_commit();
        wgmma_wait<1>();
        if (t > 0 && (threadIdx.x & 127) == 0) mbar_arrive(t < 9 ? bars + 8 * (A1_NST + (t - 1) % A1_NST) : bars + 144);
    }
}

__global__ void __launch_bounds__(A1_THREADS, 1) a1_kernel(const int layer, const bf16* __restrict__ x0, const __grid_constant__ CUtensorMap tmX,
                                                           const __grid_constant__ CUtensorMap tmR, const __grid_constant__ CUtensorMap tmOst) {
    extern __shared__ unsigned char smraw[];
    const uint32_t sbase = (smem_u32(smraw) + 1023) & ~1023u;
    const uint32_t bars = sbase + A1_SM_BAR;
    const uint32_t bar_stat = bars + 64, bar_kv = bars + 72, bar_r = bars + 152;
    const int tid = threadIdx.x, w = __shfl_sync(~0u, tid >> 5, 0), wg = w >> 2;
    const int tile = sm_tile();
    if (tile >= 128) { sm_idle(2 * layer); return; }
    const int mb = (tile >> 2) & 15, hg = 4 * (tile >> 6) + (tile & 3);
    unsigned char* stg = smraw + (sbase - smem_u32(smraw));
    float* cs = reinterpret_cast<float*>(stg + A1_SM_CS);
    float2* rst = reinterpret_cast<float2*>(stg + A1_SM_RS);
    const int pre = layer ? A1_PRE1 : A1_PRE0;
    auto issue_w = [&](int kb) {
        bulk_load(sbase + (kb % A1_NST) * A1_STAGE + 16384, reinterpret_cast<const unsigned char*>(g_wq) + (hg * 10 + kb) * WQ_STAGE, WQ_STAGE, bars + 8 * (kb % A1_NST));
    };
    auto issue_x = [&](int kb) {
        const uint32_t dst = sbase + (kb % A1_NST) * A1_STAGE, full = bars + 8 * (kb % A1_NST);
        if (layer == 0) tma_load_2d(dst, &tmX, kb * 64, mb * 128, full);
        else { tma_load_2d(dst, &tmX, mb * 128, kb * 64, full); tma_load_2d(dst + 8192, &tmX, mb * 128 + 64, kb * 64, full); }
    };
    if (w == 8) {
        if (tid == 256) {
            prefetch_tmap(&tmX);
#pragma unroll
            for (int i = 0; i < A1_NST; i++) { mbar_init(bars + 8 * i, 1); mbar_init(bars + 8 * (A1_NST + i), 2); }
            mbar_init(bar_r, 1);
            asm volatile("fence.mbarrier_init.release.cluster;" ::: "memory");
#pragma unroll
            for (int i = 0; i < A1_NST; i++) mbar_expect_tx(bars + 8 * i, A1_STAGE);
            mbar_expect_tx(bar_r, 20480);
        }
        __syncwarp();
        asm volatile("bar.arrive 0, 384;" ::: "memory");
        if (tid == 256) {
#pragma unroll 1
            for (int kb = 0; kb < pre; kb++) { if (layer) issue_w(kb); else issue_x(kb); }
            pdl_sync();
#pragma unroll 1
            for (int kb = 0; kb < A1_NST; kb++) {
                if (kb == A1_SDELAY && layer) {
                    tma_load_2d(sbase + A1_SM_R, &tmR, mb * 128, hg * 80, bar_r); tma_load_2d(sbase + A1_SM_R + 10240, &tmR, mb * 128 + 64, hg * 80, bar_r);
                }
                if (kb >= pre || layer) issue_x(kb);
                if (kb >= pre || !layer) issue_w(kb);
            }
        }
    } else {
        if (tid == 0) {
            mbar_init(bar_stat, 4);
#pragma unroll
            for (int i = 0; i < 9; i++) mbar_init(bar_kv + 8 * i, i ? 1 : 4);
            mbar_init(bars + 144, 2);
            asm volatile("fence.mbarrier_init.release.cluster;" ::: "memory");
        } else if (tid == 320) { prefetch_tmap(&tmR); prefetch_tmap(&tmOst); }
        asm volatile("bar.sync 0, 384;" ::: "memory");
    }
    SPAN(1 + 4 * layer, 0);
    const uint32_t tag = ld_epoch();
    if (tid == 352) sm_started(2 * layer);
    if (wg == 2) {
        const bool is_producer = (tid == 256);
        const int t = tid - 256;
        if (layer && w > 8) pdl_sync();
        if (tid >= 288) {
            const int j = tid - 288;
            if (layer == 0) {
                float* red = reinterpret_cast<float*>(stg + A1_SM_RED);
                const int r = j / 6, c6 = j - 6 * r;
                const uint4* src = reinterpret_cast<const uint4*>(x0 + (size_t)(mb * 128 + hg * 16 + r) * DM);
                uint4 v[14];
#pragma unroll
                for (int k = 0; k < 14; k++) v[k] = __ldg(src + min(c6 + 6 * k, 79));
                const float p0 = __uint_as_float(__ldg(reinterpret_cast<const uint32_t*>(src)) << 16);
                float s[2] = {0.f, 0.f}, q[2] = {0.f, 0.f};
#pragma unroll
                for (int k = 0; k < 14; k++) {
                    const uint32_t w[4] = {v[k].x, v[k].y, v[k].z, v[k].w};
                    if (k < 13 || c6 < 2) {
#pragma unroll
                        for (int i = 0; i < 4; i++) {
                            const float a = __uint_as_float(w[i] << 16) - p0, b = __uint_as_float(w[i] & 0xffff0000u) - p0;
                            s[0] += a; s[1] += b; q[0] = fmaf(a, a, q[0]); q[1] = fmaf(b, b, q[1]);
                        }
                    }
                }
                red[j] = s[0] + s[1]; red[96 + j] = q[0] + q[1]; red[192 + j] = p0;
                asm volatile("bar.sync 2, 96;" ::: "memory");
                if (j < 16) {
                    float s0 = 0.f, q0 = 0.f;
#pragma unroll
                    for (int k = 0; k < 6; k++) { s0 += red[6 * j + k]; q0 += red[96 + 6 * j + k]; }
                    const float d = s0 * (1.0f / DM);
                    const uint32_t ms = pack2(red[192 + 6 * j] + d, rbf(sqrtf(rbf(rbf(fmaxf(fmaf(-d, d, q0 * (1.0f / DM)), 0.f)) + 1e-5f))));
                    asm volatile("st.global.cg.u64 [%0], %1;" ::"l"(g_rstat + mb * 128 + hg * 16 + j), "l"(tagw(ms, tag)) : "memory");
                    g_piv[mb * 128 + hg * 16 + j] = __ushort_as_bfloat16((unsigned short)ms);
                }
                pdl_sync();
            } else if (j >= 32) {
                const int ch = j & 7, kg = (j >> 3) & 3;
                const unsigned char* src = stg + A1_SM_R + ((j >> 5) - 1) * 10240;
                mbar_wait(bar_r, 0);
                uint4 v[20];
#pragma unroll
                for (int k = 0; k < 20; k++) v[k] = *reinterpret_cast<const uint4*>(src + (4 * k + kg) * 128 + ((ch ^ ((4 * k + kg) & 7)) << 4));
                const uint4 pv = *reinterpret_cast<const uint4*>(src + (ch << 4));
                float s[8], q[8], p0[8] = {__uint_as_float(pv.x << 16), __uint_as_float(pv.x & 0xffff0000u), __uint_as_float(pv.y << 16), __uint_as_float(pv.y & 0xffff0000u),
                                           __uint_as_float(pv.z << 16), __uint_as_float(pv.z & 0xffff0000u), __uint_as_float(pv.w << 16), __uint_as_float(pv.w & 0xffff0000u)};
#pragma unroll
                for (int i = 0; i < 8; i++) { s[i] = 0.f; q[i] = 0.f; }
#pragma unroll
                for (int k = 0; k < 20; k++) {
                    const uint32_t w[4] = {v[k].x, v[k].y, v[k].z, v[k].w};
#pragma unroll
                    for (int i = 0; i < 4; i++) {
                        const float a = __uint_as_float(w[i] << 16) - p0[2 * i], b = __uint_as_float(w[i] & 0xffff0000u) - p0[2 * i + 1];
                        s[2 * i] += a; s[2 * i + 1] += b; q[2 * i] = fmaf(a, a, q[2 * i]); q[2 * i + 1] = fmaf(b, b, q[2 * i + 1]);
                    }
                }
#pragma unroll
                for (int i = 0; i < 4; i++) {
                    const bool up = kg & 2;
                    const float ss = __shfl_xor_sync(~0u, up ? s[i] : s[i + 4], 16), qq = __shfl_xor_sync(~0u, up ? q[i] : q[i + 4], 16);
                    s[i] = (up ? s[i + 4] : s[i]) + ss; q[i] = (up ? q[i + 4] : q[i]) + qq; p0[i] = up ? p0[i + 4] : p0[i];
                }
#pragma unroll
                for (int i = 0; i < 2; i++) {
                    const bool up = kg & 1;
                    const float ss = __shfl_xor_sync(~0u, up ? s[i] : s[i + 2], 8), qq = __shfl_xor_sync(~0u, up ? q[i] : q[i + 2], 8);
                    s[i] = (up ? s[i + 2] : s[i]) + ss; q[i] = (up ? q[i + 2] : q[i]) + qq; p0[i] = up ? p0[i + 2] : p0[i];
                }
#pragma unroll
                for (int r = 0; r < 2; r++) {
                    const float d = s[r] * (1.0f / 80.0f);
                    st_tag2(g_part + (mb * 8 + hg) * 128 + 64 * r + j - 32, __float_as_uint(p0[r] + d), __float_as_uint(fmaxf(fmaf(-d, s[r], q[r]), 0.f)), tag);
                }
            }
            TSTAMP1T(12, 320);
            if (j < 32) {
#pragma unroll
                for (int h = 0; h < 2; h++) {
                    const int i = j + 32 * h;
                    if (i < 60) {
                        float4 a = make_float4(0.f, 0.f, 0.f, 0.f);
#pragma unroll
                        for (int k = 0; k < 10; k++) {
                            const float4 v = __ldcg(reinterpret_cast<const float4*>(g_csp + k * 1920 + hg * 240) + i);
                            a.x += v.x; a.y += v.y; a.z += v.z; a.w += v.w;
                        }
                        reinterpret_cast<float4*>(cs)[i] = a;
                    }
                }
                TSTAMP1T(13, 288);
            } else if (layer == 0) {
                ulonglong2 v;
#pragma unroll 1
                for (int it = 0; it < SPIN_MAX; it++) {
                    v = ld_tag2(reinterpret_cast<const ulonglong2*>(g_rstat + mb * 128) + j - 32);
                    if (tag_ok(v, tag)) break;
                    __nanosleep(100);
                }
                *reinterpret_cast<float4*>(rst + 2 * (j - 32)) = make_float4(__uint_as_float((uint32_t)v.x << 16), __frcp_rn(__uint_as_float((uint32_t)v.x & 0xffff0000u)),
                                                                             __uint_as_float((uint32_t)v.y << 16), __frcp_rn(__uint_as_float((uint32_t)v.y & 0xffff0000u)));
            } else {
                const ulonglong2* gp = g_part + mb * 8 * 128 + j - 32;
#pragma unroll 1
                for (int it = 0; it < SPIN_MAX; it++) {
                    if (__all_sync(~0u, tag_ok(ld_tag2(gp + (j & 7) * 128 + 64), tag))) break;
                    __nanosleep(200);
                }
                ulonglong2 pv[16];
#pragma unroll 1
                for (int it = 0; it < SPIN_MAX; it++) {
                    bool ok = true;
#pragma unroll
                    for (int k = 0; k < 16; k++) pv[k] = ld_tag2(gp + k * 64);
#pragma unroll
                    for (int k = 0; k < 16; k++) ok = ok && tag_ok(pv[k], tag);
                    if (ok) break;
                    __nanosleep(200);
                }
                float o[4];
#pragma unroll
                for (int r = 0; r < 2; r++) {
                    float mean = 0.f, m2 = 0.f;
#pragma unroll
                    for (int k = 0; k < 8; k++) mean += __uint_as_float((uint32_t)pv[2 * k + r].x);
                    mean *= 0.125f;
#pragma unroll
                    for (int k = 0; k < 8; k++) {
                        const float dm = __uint_as_float((uint32_t)pv[2 * k + r].x) - mean;
                        m2 += fmaf(80.0f * dm, dm, __uint_as_float((uint32_t)pv[2 * k + r].y));
                    }
                    o[2 * r] = rbf(mean);
                    o[2 * r + 1] = __frcp_rn(rbf(sqrtf(rbf(rbf(m2 * (1.0f / DM)) + 1e-5f))));
                }
                const int row = ((j >> 5) - 1) * 64 + (j & 7) * 8 + ((j >> 3) & 3) * 2;
                *reinterpret_cast<float4*>(rst + row) = make_float4(o[0], o[1], o[2], o[3]);
                if (hg == 0) *reinterpret_cast<uint32_t*>(g_piv + SEQ + mb * 128 + row) = __byte_perm(__float_as_uint(o[0]), __float_as_uint(o[2]), 0x7632);
            }
            TSTAMP1T(7, 320);
        } else if (is_producer) {
            for (int kb = A1_NST; kb < 10; kb++) {
                mbar_wait(bars + 8 * (A1_NST + kb % A1_NST), ((kb / A1_NST) - 1) & 1);
                mbar_expect_tx(bars + 8 * (kb % A1_NST), A1_STAGE);
                issue_x(kb); issue_w(kb);
            }
            TSTAMP1T(6, 256);
        }
        __syncwarp();
        if ((tid & 31) == 0) mbar_arrive(bar_stat);
        mbar_wait(bars + 144, 0);
        mbar_wait(bars + 8 * (A1_NST + 3), 1);
        TSTAMP1T(9, 256);
        const ulonglong2* hin = g_halo + ((size_t)(layer * 16 + mb - 1) * 8 + hg) * 640 + t;
        ulonglong2 hv[5];
        if (mb > 0) {
#pragma unroll 1
            for (int it = 0; it < SPIN_MAX; it++) {
                bool ok = true;
#pragma unroll
                for (int k = 0; k < 5; k++) hv[k] = ld_tag2(hin + 128 * k);
#pragma unroll
                for (int k = 0; k < 5; k++) ok = ok && tag_ok(hv[k], tag);
                if (ok) break;
            }
        } else {
#pragma unroll
            for (int k = 0; k < 5; k++) hv[k] = make_ulonglong2(0, 0);
        }
        TSTAMP1T(11, 256);
        unsigned char* hd = stg + A1_SM_KV + ((t & 31) >> 2) * A1_KVP + (t & 3) * 4 + (t >> 5) * 16;
#pragma unroll
        for (int k = 0; k < 5; k++) {
            *reinterpret_cast<uint32_t*>(hd + 64 * k) = (uint32_t)hv[k].x;
            *reinterpret_cast<uint32_t*>(hd + 64 * k + 8 * A1_KVP) = (uint32_t)hv[k].y;
        }
        __syncwarp();
        if ((tid & 31) == 0) mbar_arrive(bar_kv);
    } else {
        pdl_sync();
        SPAN(1 + 4 * layer, 1);
        TSTAMP1(0);
        if (threadIdx.x == 0) { GSTAMP(g_tim1, 15); }
        TSTAMP3(0);
        float acc[120];
#pragma unroll
        for (int i = 0; i < 120; i++) acc[i] = 0.f;
        if (layer == 0) a1_mainloop<0>(acc, sbase, bars, wg, tile); else a1_mainloop<1>(acc, sbase, bars, wg, tile);
        const int lane = tid & 31, warp = w, g = lane >> 2, t = lane & 3;
        mbar_wait(bar_stat, 0);
        mbar_wait(bars + 8 * (A1_NST + 3), 1);
        const float2 sa_ = rst[16 * warp + g], sb_ = rst[16 * warp + g + 8];
        wgmma_wait<0>();
        TSTAMP1(2);
        uint32_t f[30][2];
        auto norm = [&](int j0) {
            float2 cc[10];
#pragma unroll
            for (int j = 0; j < 10; j++) cc[j] = *reinterpret_cast<const float2*>(cs + 8 * (j0 + j) + 2 * t);
#pragma unroll
            for (int j = 0; j < 10; j++) {
                const float* a = acc + 4 * (j0 + j);
                f[j0 + j][0] = pack2(fmaf(-sa_.x, cc[j].x, a[0]) * sa_.y, fmaf(-sa_.x, cc[j].y, a[1]) * sa_.y);
                f[j0 + j][1] = pack2(fmaf(-sb_.x, cc[j].x, a[2]) * sb_.y, fmaf(-sb_.x, cc[j].y, a[3]) * sb_.y);
            }
        };
        norm(10); norm(20);
        if (warp == 7) {
            ulonglong2* hout = g_halo + ((size_t)(layer * 16 + mb) * 8 + hg) * 640 + lane;
#pragma unroll
            for (int j = 0; j < 20; j++) st_tag2(hout + 32 * j, f[10 + j][0], f[10 + j][1], tag);
        }
        const uint32_t kvw = sbase + A1_SM_KV + 16 * warp * A1_KVP;
        const uint32_t mrow = kvw + (lane & 15) * A1_KVP + (lane >> 4) * 16;
#pragma unroll
        for (int j = 0; j < 20; j += 2) stsm_x4(mrow + 16 * A1_KVP + 16 * j, f[10 + j][0], f[10 + j][1], f[11 + j][0], f[11 + j][1]);
        __syncwarp();
        if (lane == 0) mbar_arrive(bar_kv + 8 * (warp + 1));
        norm(0);
        TSTAMP1T(10, 64);
        float sc[4][4][4];
        uint32_t qs[4][2];
#pragma unroll
        for (int h = 0; h < 4; h++) {
            const int jb = 5 * (h >> 1) + 3 * (h & 1), js = 5 * (h >> 1) + 2;
            qs[h][0] = (t >> 1) == (h & 1) ? f[js][0] : 0u; qs[h][1] = (t >> 1) == (h & 1) ? f[js][1] : 0u;
#pragma unroll
            for (int nt = 2; nt < 4; nt++) {
#pragma unroll
                for (int e = 0; e < 4; e++) sc[h][nt][e] = 0.f;
                mma_bf16(sc[h][nt], f[jb][0], f[jb][1], f[jb + 1][0], f[jb + 1][1], f[10 + jb][nt - 2], f[11 + jb][nt - 2]);
                mma_bf16_k8(sc[h][nt], qs[h][0], qs[h][1], f[10 + js][nt - 2]);
            }
        }
        mbar_wait(bar_kv + 8 * warp, 0);
        TSTAMP1(8);
        uint32_t kp[10][2];
#pragma unroll
        for (int j = 0; j < 10; j += 2) ldsm_x4(&kp[j][0], mrow + 16 * j);
#pragma unroll
        for (int h = 0; h < 4; h++) {
            const int jb = 5 * (h >> 1) + 3 * (h & 1), js = 5 * (h >> 1) + 2;
#pragma unroll
            for (int nt = 0; nt < 2; nt++) {
#pragma unroll
                for (int e = 0; e < 4; e++) sc[h][nt][e] = 0.f;
                mma_bf16(sc[h][nt], f[jb][0], f[jb][1], f[jb + 1][0], f[jb + 1][1], kp[jb][nt], kp[jb + 1][nt]);
                mma_bf16_k8(sc[h][nt], qs[h][0], qs[h][1], kp[js][nt]);
            }
        }
        uint32_t vb[10][4];
#pragma unroll
        for (int j = 0; j < 10; j++) ldsm_x4_t(vb[j], kvw + lane * A1_KVP + 160 + 16 * j);
        TSTAMP1T(3, 64);
        const bool odd = g & 1, hi = t > (g >> 1), edge = (mb | warp) == 0;
        float p[4][4], mx[4][2], sum[4][2];
#pragma unroll
        for (int h = 0; h < 4; h++) {
#pragma unroll
            for (int r = 0; r < 2; r++) {
                const float a = odd ? sc[h][1 + r][2 * r + 1] : sc[h][1 + r][2 * r];
                const float b0 = odd ? sc[h][r][2 * r + 1] : sc[h][r][2 * r], b1 = odd ? sc[h][2 + r][2 * r + 1] : sc[h][2 + r][2 * r];
                const uint32_t w = pack2(a, hi ? b0 : b1);
                const uint32_t w2 = pack2(__uint_as_float(w << 16) * 0.22360679774997896f, __uint_as_float(w & 0xffff0000u) * 0.22360679774997896f);
                p[h][2 * r] = __uint_as_float(w2 << 16); p[h][2 * r + 1] = __uint_as_float(w2 & 0xffff0000u);
            }
            if (edge) {
                p[h][0] = -1.0e9f;
                if (hi) { p[h][1] = -1.0e9f; p[h][3] = -1.0e9f; }
            }
            mx[h][0] = fmaxf(p[h][0], p[h][1]); mx[h][1] = fmaxf(p[h][2], p[h][3]);
        }
#pragma unroll
        for (int o = 1; o <= 2; o <<= 1)
#pragma unroll
            for (int h = 0; h < 4; h++)
#pragma unroll
                for (int r = 0; r < 2; r++) mx[h][r] = fmaxf(mx[h][r], __shfl_xor_sync(~0u, mx[h][r], o));
#pragma unroll
        for (int h = 0; h < 4; h++)
#pragma unroll
            for (int r = 0; r < 2; r++) {
                p[h][2 * r] = __expf(p[h][2 * r] - mx[h][r]); p[h][2 * r + 1] = __expf(p[h][2 * r + 1] - mx[h][r]);
                sum[h][r] = p[h][2 * r] + p[h][2 * r + 1];
            }
#pragma unroll
        for (int o = 1; o <= 2; o <<= 1)
#pragma unroll
            for (int h = 0; h < 4; h++)
#pragma unroll
                for (int r = 0; r < 2; r++) sum[h][r] += __shfl_xor_sync(~0u, sum[h][r], o);
        TSTAMP1T(5, 64);
        const uint32_t selA = odd ? 0x1044u : 0x4410u, selB = odd ? 0x3244u : 0x4432u, selH = hi ? selB : 0x4444u, selL = hi ? 0x4444u : selB;
        const uint32_t orow = sbase + A1_SM_O + (16 * warp + (lane & 15)) * 160 + (lane >> 4) * 16;
        uint32_t ob[10][2];
#pragma unroll
        for (int P = 0; P < 2; P++) {
            float os[2][4];
#pragma unroll
            for (int e = 0; e < 2; e++) {
                const int h = 2 * P + e;
                const float i0 = __fdividef(1.0f, sum[h][0]), i1 = __fdividef(1.0f, sum[h][1]);
                const uint32_t w0 = pack2(p[h][0] * i0, p[h][1] * i0), w1 = pack2(p[h][2] * i1, p[h][3] * i1);
                const uint32_t a00 = __byte_perm(w0, 0, selH), a02 = __byte_perm(w0, 0, selA), a03 = __byte_perm(w1, 0, selH);
                const uint32_t a10 = __byte_perm(w0, 0, selL), a11 = __byte_perm(w1, 0, selA), a13 = __byte_perm(w1, 0, selL);
#pragma unroll
                for (int dt = 0; dt < 3; dt++) {
                    const int j = 5 * P + (dt < 2 ? 3 * e + dt : 2);
                    float o[4] = {0.f, 0.f, 0.f, 0.f};
                    mma_bf16(o, a00, 0u, a02, a03, vb[j][0], vb[j][1]);
                    mma_bf16(o, a10, a11, 0u, a13, vb[j][2], vb[j][3]);
                    if (dt < 2) { ob[j][0] = pack2(o[0], o[1]); ob[j][1] = pack2(o[2], o[3]); }
                    else { os[e][0] = o[0]; os[e][1] = o[1]; os[e][2] = o[2]; os[e][3] = o[3]; }
                }
            }
            ob[5 * P + 2][0] = t < 2 ? pack2(os[0][0], os[0][1]) : pack2(os[1][0], os[1][1]);
            ob[5 * P + 2][1] = t < 2 ? pack2(os[0][2], os[0][3]) : pack2(os[1][2], os[1][3]);
        }
#pragma unroll
        for (int j = 0; j < 10; j += 2) stsm_x4(orow + 16 * j, ob[j][0], ob[j][1], ob[j + 1][0], ob[j + 1][1]);
        fence_async_smem();
        __syncwarp();
        if (lane == 0) tma_store_2d(&tmOst, hg * 80, mb * 128 + 16 * warp, sbase + A1_SM_O + 16 * warp * 160);
        TSTAMP1T(4, 64);
        TSTAMP1(1);
        GSTAMP(g_tim1, 14);
        SPAN(1 + 4 * layer, 3);
    }
}

constexpr int A2_THREADS = 288;
constexpr int A2_NA = 6;
#define A2_WPRE 4
#define A2_WLEAD 2
#define A2_RPOS 7
constexpr int A2_SM_A = 10 * WO_STAGE;
constexpr int A2_SM_R = A2_SM_A + A2_NA * 16384;
constexpr int A2_SM_BAR = A2_SM_R + 20480;
constexpr int A2_SMEM = A2_SM_BAR + 256 + 1024;

__global__ void __launch_bounds__(A2_THREADS, 1) a2_kernel(const int layer, const __grid_constant__ CUtensorMap tmO, const __grid_constant__ CUtensorMap tmR,
                                                           const __grid_constant__ CUtensorMap tmX1) {
    extern __shared__ unsigned char smraw[];
    const uint32_t sbase = (smem_u32(smraw) + 1023) & ~1023u;
    const uint32_t bars = sbase + A2_SM_BAR, bar_e = bars + 80, bar_r = bars + 128;
    const int tid = threadIdx.x, w = __shfl_sync(~0u, tid >> 5, 0), wg = w >> 2;
    const int tile = sm_tile();
    if (tile >= 128) { sm_idle(2 * layer + 1); return; }
    const int mb = tile >> 3, cg = tile & 7;
    if (wg == 2) {
        const unsigned char* wsrc = reinterpret_cast<const unsigned char*>(g_wo) + cg * 10 * WO_STAGE;
        if (tid == 256) {
            prefetch_tmap(&tmO);
#pragma unroll
            for (int i = 0; i < 17; i++) mbar_init(bars + 8 * i, i >= 10 && i < 16 ? 2 : 1);
            asm volatile("fence.mbarrier_init.release.cluster;" ::: "memory");
#pragma unroll
            for (int kb = 0; kb < A2_WPRE; kb += 2) {
                mbar_expect_tx(bars + 8 * kb, 16384 + 2 * WO_STAGE);
                bulk_load(sbase + kb * WO_STAGE, wsrc + kb * WO_STAGE, 2 * WO_STAGE, bars + 8 * kb);
            }
        }
        __syncwarp();
        asm volatile("bar.arrive 0, 288;" ::: "memory");
        if (tid == 256) {
#pragma unroll
            for (int kb = 0; kb < 10; kb++) if ((kb & 1) || kb >= A2_WPRE) mbar_expect_tx(bars + 8 * kb, (kb & 1) ? 16384 : 16384 + 2 * WO_STAGE);
            mbar_expect_tx(bar_r, 20480);
            pdl_sync();
#pragma unroll 1
            for (int kb = 0; kb < 10; kb++) {
                if (kb >= A2_NA) mbar_wait(bar_e + 8 * (kb - A2_NA), 0);
                tma_load_2d(sbase + A2_SM_A + (kb < A2_NA ? kb : kb - A2_NA) * 16384, &tmO, kb * 64, mb * 128, bars + 8 * kb);
                const int kw = kb + A2_WLEAD;
                if (!(kw & 1) && kw >= A2_WPRE && kw < 10) bulk_load(sbase + kw * WO_STAGE, wsrc + kw * WO_STAGE, 2 * WO_STAGE, bars + 8 * kw);
                if (kb == A2_RPOS) {
                    if (layer == 0) tma_load_2d(sbase + A2_SM_R, &tmR, cg * 80, mb * 128, bar_r);
                    else { tma_load_2d(sbase + A2_SM_R, &tmR, mb * 128, cg * 80, bar_r); tma_load_2d(sbase + A2_SM_R + 10240, &tmR, mb * 128 + 64, cg * 80, bar_r); }
                }
            }
        }
    } else {
        if (tid == 224) { prefetch_tmap(&tmR); prefetch_tmap(&tmX1); sm_started(2 * layer + 1); }
        asm volatile("bar.sync 0, 288;" ::: "memory");
        SPAN(2 + 4 * layer, 0);
        pdl_sync();
        SPAN(2 + 4 * layer, 1);
        TSTAMP2(0);
        TSTAMP4(0);
        if (threadIdx.x == 0) { GSTAMP(g_tim2, 15); }
        const int lane = tid & 31, warp = w, g = lane >> 2, t = lane & 3;
        const int row = layer * SEQ + mb * 128 + 16 * warp + g;
        const unsigned short pv0 = __ldcg(reinterpret_cast<const unsigned short*>(g_piv) + row), pv1 = __ldcg(reinterpret_cast<const unsigned short*>(g_piv) + row + 8);
        float acc[40];
#pragma unroll
        for (int i = 0; i < 40; i++) acc[i] = 0.f;
        const uint64_t da0 = make_desc(sbase + A2_SM_A + wg * 8192, 16, 1024, 1), db0 = make_desc(sbase, 16, 1024, 1);
#pragma unroll 1
        for (int kb = 0; kb < 10; kb++) {
            if (kb == 0) TSTAMP4(11);
            mbar_wait(bars + 8 * kb, 0);
            TSTAMP4(1 + kb);
            wgmma_fence();
#pragma unroll
            for (int kk = 0; kk < 4; kk++) wgmma_n80<0, 0>(acc, da0 + (uint32_t)((kb < A2_NA ? kb : kb - A2_NA) * 1024 + kk * 2), db0 + (uint32_t)(kb * (WO_STAGE / 16) + kk * 2));
            wgmma_commit();
            wgmma_wait<1>();
            if (kb > 0 && kb <= A2_NA && (tid & 127) == 0) mbar_arrive(bar_e + 8 * (kb - 1));
        }
        const uint32_t trow = ((lane & 7) + 8 * (lane >> 4)) * 128 + (((2 * (warp & 3) + ((lane >> 3) & 1)) ^ (lane & 7)) << 4);
        uint32_t xr[10][2];
        mbar_wait(bar_r, 0);
        if (layer == 0) {
#pragma unroll
            for (int j = 0; j < 10; j += 2) ldsm_x4(&xr[j][0], sbase + A2_SM_R + (16 * warp + (lane & 15)) * 160 + (lane >> 4) * 16 + 16 * j);
        } else {
#pragma unroll
            for (int j = 0; j < 10; j += 2) ldsm_x4_t(&xr[j][0], sbase + A2_SM_R + wg * 10240 + trow + 1024 * j);
        }
        mbar_wait(bar_e + 8 * (4 + wg), 0);
        wgmma_wait<0>();
        TSTAMP2(1);
        const float p0 = __uint_as_float((uint32_t)pv0 << 16), p1 = __uint_as_float((uint32_t)pv1 << 16);
        float s[4] = {0.f, 0.f, 0.f, 0.f};
#pragma unroll
        for (int j = 0; j < 10; j++) {
#pragma unroll
            for (int hh = 0; hh < 2; hh++) {
                const uint32_t a = pack2(acc[4 * j + 2 * hh], acc[4 * j + 2 * hh + 1]);
                const __nv_bfloat162 r = __hadd2_rn(*reinterpret_cast<const __nv_bfloat162*>(&xr[j][hh]), *reinterpret_cast<const __nv_bfloat162*>(&a));
                const uint32_t w = *reinterpret_cast<const uint32_t*>(&r);
                xr[j][hh] = w;
                const float d0 = __uint_as_float(w << 16) - (hh ? p1 : p0), d1 = __uint_as_float(w & 0xffff0000u) - (hh ? p1 : p0);
                s[2 * hh] += d0 + d1;
                s[2 * hh + 1] = fmaf(d0, d0, fmaf(d1, d1, s[2 * hh + 1]));
            }
        }
        const uint32_t so = sbase + A2_SM_A + (4 + wg) * 16384;
#pragma unroll
        for (int j = 0; j < 10; j += 2) stsm_x4_t(so + trow + 1024 * j, xr[j][0], xr[j][1], xr[j + 1][0], xr[j + 1][1]);
        fence_async_smem();
        TSTAMP2(2);
#pragma unroll
        for (int o = 1; o <= 2; o <<= 1)
#pragma unroll
            for (int i = 0; i < 4; i++) s[i] += __shfl_xor_sync(~0u, s[i], o);
        if (t < 2) asm volatile("red.relaxed.gpu.global.add.v2.f32 [%0], {%1, %2};" ::"l"(g_sum + layer * SEQ + (g >> 1) * 512 + (mb * 16 + 2 * warp + t) * 2 + (g & 1)), "f"(t ? s[2] : s[0]), "f"(t ? s[3] : s[1]) : "memory");
        if (wg) asm volatile("bar.sync 2, 128;" ::: "memory"); else asm volatile("bar.sync 1, 128;" ::: "memory");
        TSTAMP2(3);
        if ((tid & 127) == 0) tma_store_2d(&tmX1, mb * 128 + 64 * wg, cg * 80, so);
        TSTAMP2(4);
        GSTAMP(g_tim2, 14);
        SPAN(2 + 4 * layer, 3);
    }
}

static int h_nsm;
static CUtensorMap h_tmX0, h_tmX1, h_tmOst, h_tmO, h_tmR0, h_tmR1, h_tmX1st, h_tmOut;
typedef CUresult (*PFN_encodeTiled)(CUtensorMap*, CUtensorMapDataType, cuuint32_t, void*, const cuuint64_t*, const cuuint64_t*,
                                    const cuuint32_t*, const cuuint32_t*, CUtensorMapInterleave, CUtensorMapSwizzle,
                                    CUtensorMapL2promotion, CUtensorMapFloatOOBfill);
static void make_tmap(CUtensorMap* tm, const void* ptr, uint64_t cols, uint64_t rows, uint32_t bc, uint32_t br, CUtensorMapSwizzle sw, uint64_t pitch = 0) {
    static PFN_encodeTiled fn = nullptr;
    if (!fn) {
        void* p = nullptr; cudaDriverEntryPointQueryResult qr;
        cudaGetDriverEntryPoint("cuTensorMapEncodeTiled", &p, cudaEnableDefault, &qr);
        fn = (PFN_encodeTiled)p;
    }
    cuuint64_t dims[2] = {cols, rows}; cuuint64_t strides[1] = {(pitch ? pitch : cols) * 2};
    cuuint32_t box[2] = {bc, br}; cuuint32_t es[2] = {1, 1};
    fn(tm, CU_TENSOR_MAP_DATA_TYPE_BFLOAT16, 2, const_cast<void*>(ptr), dims, strides, box, es, CU_TENSOR_MAP_INTERLEAVE_NONE, sw,
       CU_TENSOR_MAP_L2_PROMOTION_L2_128B, CU_TENSOR_MAP_FLOAT_OOB_FILL_NONE);
}
template <typename... Args>
static void launch_pdl(void (*kern)(Args...), int grid, int block, int smem, Args... args) {
    cudaLaunchConfig_t cfg = {};
    cfg.gridDim = dim3(grid); cfg.blockDim = dim3(block); cfg.dynamicSmemBytes = smem; cfg.stream = cudaStreamPerThread;
    cudaLaunchAttribute at[1];
    at[0].id = cudaLaunchAttributeProgrammaticStreamSerialization; at[0].val.programmaticStreamSerializationAllowed = 1;
    cfg.attrs = at; cfg.numAttrs = 1;
    cudaLaunchKernelEx(&cfg, kern, args...);
}
static void launch_stage(int k, void* const* d_in, void* d_out) {
    const KgIn kg = {(const bf16*)d_in[4], (const bf16*)d_in[5], (const bf16*)d_in[6], (const bf16*)d_in[7], (const bf16*)d_in[8], (const bf16*)d_in[0], (const bf16*)d_in[1], (const bf16*)d_in[2]};
    switch (k) {
        case 0: kgen_kernel<<<DM, KG_THREADS, 0, cudaStreamPerThread>>>(kg); break;
        case 1: launch_pdl(a1_kernel, h_nsm, A1_THREADS, A1_SMEM, 0, (const bf16*)d_in[0], h_tmX0, h_tmR1, h_tmOst); break;
        case 2: launch_pdl(a2_kernel, h_nsm, A2_THREADS, A2_SMEM, 0, h_tmO, h_tmR0, h_tmX1st); break;
        case 3: launch_pdl(conv_kernel, DM / CV_CPB, CV_THREADS, CV_SMEM, (const bf16*)d_in[9], 0, h_tmOut); break;
        case 5: launch_pdl(a1_kernel, h_nsm, A1_THREADS, A1_SMEM, 1, (const bf16*)d_in[0], h_tmX1, h_tmR1, h_tmOst); break;
        case 6: launch_pdl(a2_kernel, h_nsm, A2_THREADS, A2_SMEM, 1, h_tmO, h_tmR1, h_tmX1st); break;
        case 7: launch_pdl(conv_kernel, DM / CV_CPB, CV_THREADS, CV_SMEM, (const bf16*)d_in[9], 1, h_tmOut); break;
        default: break;
    }
}
static int n_stage_kernels() { return 9; }
static const char* stage_name(int k) { const char* n[] = {"kgen", "a1", "a2", "conv", "tr", "a1", "a2", "conv", "tr"}; return n[k]; }

extern "C" void kernel_launch(void* const* d_in, const int* in_sizes, int n_in, void* d_out, int out_size) {
    (void)in_sizes; (void)n_in; (void)out_size;
    static const void *p_in = nullptr, *p_out = nullptr;
    if (p_in != d_in[0] || p_out != d_out) {
        cudaFuncSetAttribute(conv_kernel, cudaFuncAttributeMaxDynamicSharedMemorySize, CV_SMEM);
        cudaFuncSetAttribute(kgen_kernel, cudaFuncAttributePreferredSharedMemoryCarveout, 100);
        cudaFuncSetAttribute(a1_kernel, cudaFuncAttributeMaxDynamicSharedMemorySize, A1_SMEM);
        cudaFuncSetAttribute(a2_kernel, cudaFuncAttributeMaxDynamicSharedMemorySize, A2_SMEM);
        int dev; cudaGetDevice(&dev); cudaDeviceGetAttribute(&h_nsm, cudaDevAttrMultiProcessorCount, dev);
        if (h_nsm != 132) h_nsm = 128;
        void *po, *px1, *px2;
        cudaGetSymbolAddress(&po, g_o); cudaGetSymbolAddress(&px1, g_x1T); cudaGetSymbolAddress(&px2, g_xcT);
        make_tmap(&h_tmO, po, 640, 2048, 64, 128, CU_TENSOR_MAP_SWIZZLE_128B);
        make_tmap(&h_tmOst, po, 640, 2048, 80, 16, CU_TENSOR_MAP_SWIZZLE_NONE);
        make_tmap(&h_tmX0, d_in[0], 640, 2048, 64, 128, CU_TENSOR_MAP_SWIZZLE_128B);
        make_tmap(&h_tmX1, px2, 2048, 640, 64, 64, CU_TENSOR_MAP_SWIZZLE_128B, XCP);
        make_tmap(&h_tmR0, d_in[0], 640, 2048, 80, 128, CU_TENSOR_MAP_SWIZZLE_NONE);
        make_tmap(&h_tmR1, px2, 2048, 640, 64, 80, CU_TENSOR_MAP_SWIZZLE_128B, XCP);
        make_tmap(&h_tmX1st, px1, 2048, 640, 64, 80, CU_TENSOR_MAP_SWIZZLE_128B, XCP);
        make_tmap(&h_tmOut, d_out, 640, 2048, 80, 8, CU_TENSOR_MAP_SWIZZLE_NONE);
        p_in = d_in[0]; p_out = d_out;
    }
    for (int k = 0; k < n_stage_kernels(); k++) launch_stage(k, d_in, d_out);
}
```

```cpp
#include <cuda_runtime.h>
#include <cuda_bf16.h>
#include <stdint.h>
#include <cuda.h>

typedef __nv_bfloat16 bf16;

constexpr int SEQ = 2048;
constexpr int DM = 640;
constexpr int NMODE = 192;

__device__ __forceinline__ float bf2f(bf16 v) { return __bfloat162float(v); }
__device__ __forceinline__ float rbf(float v) {
    uint32_t r;
    asm("cvt.rn.bf16x2.f32 %0, %1, %2;" : "=r"(r) : "f"(v), "f"(0.f));
    return __uint_as_float(r);
}
__device__ __forceinline__ uint32_t pack2(float lo, float hi) {
    __nv_bfloat162 t = __floats2bfloat162_rn(lo, hi);
    return *reinterpret_cast<uint32_t*>(&t);
}
__device__ __forceinline__ void pdl_sync() {
    asm volatile("griddepcontrol.wait;" ::: "memory");
    asm volatile("griddepcontrol.launch_dependents;" ::: "memory");
}
__device__ __forceinline__ float sqrt_apx(float v) { float r; asm("sqrt.approx.ftz.f32 %0, %1;" : "=f"(r) : "f"(v)); return r; }
__device__ __forceinline__ float rcp_apx(float v) { float r; asm("rcp.approx.ftz.f32 %0, %1;" : "=f"(r) : "f"(v)); return r; }
__device__ __forceinline__ uint32_t smem_u32(const void* p) { return (uint32_t)__cvta_generic_to_shared(p); }

constexpr int TPAD = 16;
constexpr int DLEN = 544;
constexpr int TAP_W2 = DLEN * 8, TAP_W3 = TAP_W2 + 768, TAP_C = TAP_W3 + 768, TAPB = TAP_C + 384;
__device__ __align__(128) uint4 g_tap[DM * 128];
#define XPAD 64
constexpr int XCP = SEQ + XPAD;
__device__ __align__(128) bf16 g_x1T[DM * XCP];
__device__ __align__(128) bf16 g_xcT[DM * XCP];
__device__ __align__(128) bf16 g_o[SEQ * DM];
constexpr int WQ_STAGE = 240 * 128, WO_STAGE = 80 * 128;
__device__ __align__(128) uint4 g_wq[8 * 10 * WQ_STAGE / 16];
__device__ __align__(128) uint4 g_wo[8 * 10 * WO_STAGE / 16];
__device__ __align__(16) float g_csp[10 * 1920];
__device__ __align__(16) float2 g_sum[2 * SEQ];
__device__ __align__(16) bf16 g_piv[2 * SEQ];
__device__ __align__(128) bf16 g_yT[DM * XCP];
__device__ uint32_t g_epoch;
__device__ __align__(16) unsigned long long g_rstat[SEQ];
__device__ ulonglong2 g_part[16 * 8 * 128];
__device__ uint4 g_halo[2 * 128 * 320];
__device__ __forceinline__ unsigned long long tagw(uint32_t payload, uint32_t tag) { return ((unsigned long long)tag << 32) | payload; }
__device__ __forceinline__ void st_tag2(ulonglong2* p, uint32_t a, uint32_t b, uint32_t tag) {
    asm volatile("st.global.cg.v2.u64 [%0], {%1, %2};" ::"l"(p), "l"(tagw(a, tag)), "l"(tagw(b, tag)) : "memory");
}
__device__ __forceinline__ ulonglong2 ld_tag2(const ulonglong2* p) {
    ulonglong2 v;
    asm volatile("ld.relaxed.gpu.global.v2.u64 {%0, %1}, [%2];" : "=l"(v.x), "=l"(v.y) : "l"(p) : "memory");
    return v;
}
__device__ __forceinline__ bool tag_ok(ulonglong2 v, uint32_t tag) { return (uint32_t)(v.x >> 32) == tag && (uint32_t)(v.y >> 32) == tag; }
__device__ __forceinline__ uint32_t ld_epoch() { uint32_t v; asm volatile("ld.relaxed.gpu.global.u32 %0, [%1];" : "=r"(v) : "l"(&g_epoch) : "memory"); return v + 1; }
constexpr int SPIN_MAX = 1 << 20;
__device__ uint32_t g_started[4];
__device__ __forceinline__ void sm_started(int slot) { asm volatile("red.relaxed.gpu.global.add.u32 [%0], 1;" ::"l"(g_started + slot) : "memory"); }
__device__ __noinline__ void sm_idle(int slot) {
    if (threadIdx.x) return;
    sm_started(slot);
    const uint32_t want = ld_epoch() * gridDim.x;
    pdl_sync();
#pragma unroll 1
    for (int it = 0; it < SPIN_MAX; it++) {
        uint32_t v;
        asm volatile("ld.relaxed.gpu.global.u32 %0, [%1];" : "=r"(v) : "l"(g_started + slot) : "memory");
        if ((int)(v - want) >= 0) break;
        __nanosleep(100);
    }
}
__device__ __forceinline__ int sm_tile() {
    uint32_t s;
    asm volatile("mov.u32 %0, %smid;" : "=r"(s));
    const uint32_t h = (s - 64) >> 1, q = (h * 37) >> 8;
    const int t0 = ((s >> 1) & 7) * 16 + (s >> 4) * 2 + (s & 1), t1 = (1 + h - 7 * q) * 16 + 8 + q * 2 + (s & 1), t2 = s - 124 < 8 ? s - 116 : 128;
    return gridDim.x == 128 ? (int)blockIdx.x : s < 64 ? t0 : s < 120 ? t1 : t2;
}
#define DBG_SYMS
#define TSTAMP(i)
#define TSTAMP1(i)
#define TSTAMP1T(i, t)
#define TSTAMP1X(i, t)
#define SPAN(k, i)
#define GSTAMP(arr, i)
#define TSTAMP2(i)
#define TSTAMP3(i)
#define TSTAMP4(i)
#define TSTAMPK(i, t)

__device__ __forceinline__ float2 cexp_at(float wr2, float wi, float p) {
    float er;
    asm("ex2.approx.ftz.f32 %0, %1;" : "=f"(er) : "f"(wr2 * p));
    float th = wi * p;
    const float k = rintf(th * 0.15915494309189535f);
    th = fmaf(k, -6.2831854820251465f, th);
    th = fmaf(k, 1.7484555314695172e-7f, th);
    return make_float2(er * __cosf(th), er * __sinf(th));
}
__device__ __forceinline__ float2 cmul(float2 a, float2 b) {
    return make_float2(fmaf(a.x, b.x, -a.y * b.y), fmaf(a.x, b.y, a.y * b.x));
}
__device__ __forceinline__ float2 csqr(float2 a) { return make_float2(fmaf(a.x, a.x, -a.y * a.y), (a.x + a.x) * a.y); }
__device__ __forceinline__ uint32_t packh(float2 v) {
    uint32_t r;
    asm("cvt.rn.f16x2.f32 %0, %1, %2;" : "=r"(r) : "f"(v.y), "f"(v.x));
    return r;
}
__device__ __forceinline__ void mma_f16(float* d, uint32_t a0, uint32_t a1, uint32_t a2, uint32_t a3, uint32_t b0, uint32_t b1) {
    asm volatile("mma.sync.aligned.m16n8k16.row.col.f32.f16.f16.f32 {%0,%1,%2,%3}, {%4,%5,%6,%7}, {%8,%9}, {%0,%1,%2,%3};"
                 : "+f"(d[0]), "+f"(d[1]), "+f"(d[2]), "+f"(d[3]) : "r"(a0), "r"(a1), "r"(a2), "r"(a3), "r"(b0), "r"(b1));
}

struct KgIn { const bf16 *logA, *Aim, *Cre, *Cim, *logdt, *x, *wqkv, *wo; };
constexpr int KG_THREADS = NMODE / 2;

__global__ void __launch_bounds__(KG_THREADS, 5) kgen_kernel(const KgIn in) {
    __shared__ __align__(128) uint4 tab[3 * 896];
    __shared__ __align__(16) unsigned short E[1024];
    const int d = blockIdx.x, tid = threadIdx.x, lane = tid & 31, warp = tid >> 5;
    SPAN(0, 0); SPAN(0, 1);
    TSTAMPK(0, 0);
    asm volatile("griddepcontrol.launch_dependents;" ::: "memory");
    const bf16 pdt = in.logdt[d];
    const uint32_t pla = reinterpret_cast<const uint32_t*>(in.logA)[d * KG_THREADS + tid], pai = reinterpret_cast<const uint32_t*>(in.Aim)[d * KG_THREADS + tid];
    const uint32_t pcr = reinterpret_cast<const uint32_t*>(in.Cre)[d * KG_THREADS + tid], pci = reinterpret_cast<const uint32_t*>(in.Cim)[d * KG_THREADS + tid];
    const bf16* pfq = tid < 30 ? in.wqkv + (size_t)(d * 30 + tid) * 64 : tid < 40 ? in.wo + (size_t)(d * 10 + tid - 30) * 64 : in.x + (size_t)(d * 32 + tid - 40) * 64;
    if (tid < 72) asm volatile("prefetch.global.L2 [%0];" ::"l"(pfq));
    g_halo[d * 128 + tid] = make_uint4(~0u, ~0u, ~0u, ~0u);
    if (tid < 32) g_halo[d * 128 + 96 + tid] = make_uint4(~0u, ~0u, ~0u, ~0u);
    reinterpret_cast<uint4*>(E)[tid] = make_uint4(0, 0, 0, 0);
    if (tid < 32) reinterpret_cast<uint4*>(E)[96 + tid] = make_uint4(0, 0, 0, 0);
    const uint32_t tw = smem_u32(tab) + warp * 14336;
    const int g = lane >> 2, t = lane & 3;
    const uint32_t sta = tw + lane * 128 + ((2 * (lane & 3) + ((lane >> 2) & 1)) << 4);
    const uint32_t lda = tw + t * 128 + ((g ^ (2 * t)) << 4);
    const uint32_t stb = tw + 12288 + lane * 64 + ((4 * ((lane >> 1) & 1) + ((lane >> 2) & 3)) << 3);
    const uint32_t ldb = tw + 12288 + t * 64 + ((g ^ (4 * (t >> 1))) << 3);
    auto sts4 = [&](int e, int off, uint32_t a, uint32_t b, uint32_t c, uint32_t dd) {
        asm volatile("st.shared.v4.u32 [%0], {%1,%2,%3,%4};" ::"r"((sta ^ (e << 4)) + off), "r"(a), "r"(b), "r"(c), "r"(dd) : "memory");
    };
    auto lds4 = [&](int sp, int off, uint32_t* r) {
        asm volatile("ld.shared.v4.u32 {%0,%1,%2,%3}, [%4];" : "=r"(r[0]), "=r"(r[1]), "=r"(r[2]), "=r"(r[3]) : "r"((lda ^ ((sp & 1) << 4)) + sp * 512 + off) : "memory");
    };
    const float dt = rbf(expf(bf2f(pdt)));
    float2 C[2], y1[2], z8[2], y128[2];
    float cmax = 0.f;
#pragma unroll
    for (int m = 0; m < 2; m++) {
        const float wr2 = -rbf(expf(__uint_as_float(m ? pla & 0xffff0000u : pla << 16))) * dt * 1.4426950408889634f;
        const float wi = __uint_as_float(m ? pai & 0xffff0000u : pai << 16) * dt;
        C[m] = make_float2(__uint_as_float(m ? pcr & 0xffff0000u : pcr << 16) * dt, -__uint_as_float(m ? pci & 0xffff0000u : pci << 16) * dt);
        cmax = fmaxf(cmax, fmaxf(fabsf(C[m].x), fabsf(C[m].y)));
        y1[m] = cexp_at(wr2, -wi, 1.f); z8[m] = cexp_at(wr2, wi, 8.f); y128[m] = cexp_at(wr2, -wi, 128.f);
    }
    const int ex = min(max((int)(__reduce_max_sync(~0u, __float_as_uint(cmax)) >> 23), 20), 240);
    const float scale = __uint_as_float((uint32_t)(127 + 10 + 127 - ex) << 23), unscale = 2.0f * __uint_as_float((uint32_t)(ex - 10) << 23);
    TSTAMPK(4, 0);
    float k2048 = 0.f;
    {
        float2 h0[2], h1[2], g0[2], g1[2], g2[2], g2b[2], g3[2], g4[2], y2[2], y4[2];
#pragma unroll
        for (int m = 0; m < 2; m++) {
            h0[m] = make_float2(1.f, 0.f); h1[m] = csqr(csqr(csqr(z8[m])));
            g0[m] = make_float2(C[m].x * scale, C[m].y * scale);
            g1[m] = cmul(g0[m], y128[m]);
            const float2 y256 = csqr(y128[m]), y512 = csqr(y256);
            g2b[m] = g2[m] = cmul(g0[m], y256); g3[m] = cmul(g0[m], y512); g4[m] = cmul(g3[m], y512);
            y2[m] = csqr(y1[m]); y4[m] = csqr(y2[m]);
        }
#pragma unroll
        for (int e = 0; e < 8; e++) {
            sts4(e, 0, packh(h0[0]), packh(h1[0]), packh(h0[1]), packh(h1[1]));
            sts4(e, 4096, packh(g0[0]), packh(g0[1]), packh(g1[0]), packh(g1[1]));
            sts4(e, 8192, packh(g2[0]), packh(g2[1]), packh((e & 1) ? cmul(g3[0], y4[0]) : g3[0]), packh((e & 1) ? cmul(g3[1], y4[1]) : g3[1]));
            asm volatile("st.shared.v2.u32 [%0], {%1,%2};" ::"r"(stb ^ (e << 3)), "r"(packh(g4[0])), "r"(packh(g4[1])) : "memory");
#pragma unroll
            for (int m = 0; m < 2; m++) {
                if (e < 7) {
                    h0[m] = e ? cmul(h0[m], z8[m]) : z8[m]; h1[m] = cmul(h1[m], z8[m]); g0[m] = cmul(g0[m], y1[m]); g1[m] = cmul(g1[m], y1[m]);
                    g2[m] = e == 3 ? cmul(g2b[m], y128[m]) : cmul(g2[m], y2[m]);
                    if (e & 1) g3[m] = cmul(g3[m], y128[m]);
                    g4[m] = cmul(g4[m], y128[m]);
                } else k2048 += fmaf(g4[m].x, y128[m].x, -g4[m].y * y128[m].y);
            }
        }
    }
    TSTAMPK(6, 0);
    const int job = warp * DM + d;
    const bool isq = job < 1200;
    uint32_t sw[16];
    unsigned char* sdst = nullptr;
    int sn = 0;
    if (job < 1600) {
        const int j2 = isq ? job : job - 1200, kb = j2 % 10, col = (j2 / 10) * 16 + (lane >> 3) * 4;
        if (isq) {
            const int sec = col / DM, r = col - sec * DM, hg = r / 80;
            sn = hg * 160 + sec * 80 + r;
            sdst = reinterpret_cast<unsigned char*>(g_wq) + (hg * 9 + kb) * WQ_STAGE;
        } else {
            sn = col;
            sdst = reinterpret_cast<unsigned char*>(g_wo) + ((col / 80) * 9 + kb) * WO_STAGE;
        }
        const int pitch = isq ? 3 * DM : DM;
        const bf16* src = (isq ? in.wqkv : in.wo) + (size_t)(kb * 64 + (lane & 7) * 8) * pitch + col;
#pragma unroll
        for (int i = 0; i < 8; i++) {
            const uint2 v = __ldg(reinterpret_cast<const uint2*>(src + i * pitch));
            sw[2 * i] = v.x; sw[2 * i + 1] = v.y;
        }
        sn += kb << 16;
    } else if (job < 1600 + 64) {
        reinterpret_cast<uint4*>(g_sum)[(job - 1600) * 32 + lane] = make_uint4(0, 0, 0, 0);
    }
    __syncwarp();
    float acc[5][4];
#pragma unroll
    for (int j = 0; j < 5; j++)
#pragma unroll
        for (int k = 0; k < 4; k++) acc[j][k] = 0.f;
#pragma unroll
    for (int sp = 0; sp < 8; sp++) {
        uint32_t a[4], b[4], c[4], e0, e1;
        lds4(sp, 0, a); lds4(sp, 4096, b); lds4(sp, 8192, c);
        asm volatile("ld.shared.v2.u32 {%0,%1}, [%2];" : "=r"(e0), "=r"(e1) : "r"((ldb ^ ((sp & 3) << 3)) + sp * 256) : "memory");
        mma_f16(acc[0], a[0], a[1], a[2], a[3], b[0], b[1]);
        mma_f16(acc[1], a[0], a[1], a[2], a[3], b[2], b[3]);
        mma_f16(acc[2], a[0], a[1], a[2], a[3], c[0], c[1]);
        mma_f16(acc[3], a[0], a[1], a[2], a[3], c[2], c[3]);
        mma_f16(acc[4], a[0], a[1], a[2], a[3], e0, e1);
    }
#pragma unroll
    for (int o = 16; o; o >>= 1) k2048 += __shfl_xor_sync(~0u, k2048, o);
    __syncwarp();
    {
        float* Pp = reinterpret_cast<float*>(tab + warp * 896);
#pragma unroll
        for (int h = 0; h < 2; h++) {
            const int b = g + 8 * h;
            *reinterpret_cast<float2*>(Pp + 8 * b + 2 * t) = make_float2(acc[0][2 * h] * unscale, acc[0][2 * h + 1] * unscale);
            *reinterpret_cast<float2*>(Pp + 128 + 8 * b + 2 * t) = make_float2(acc[1][2 * h] * unscale, acc[1][2 * h + 1] * unscale);
            *reinterpret_cast<float2*>(Pp + 256 + 4 * b + 2 * (t & 1) + 64 * (t >> 1)) = make_float2(acc[2][2 * h] * unscale, acc[2][2 * h + 1] * unscale);
            *reinterpret_cast<float2*>(Pp + 384 + 2 * b + 32 * t) = make_float2(acc[3][2 * h] * unscale, acc[3][2 * h + 1] * unscale);
            Pp[512 + b + 32 * t] = acc[4][2 * h] * unscale;
            Pp[512 + b + 32 * t + 16] = acc[4][2 * h + 1] * unscale;
        }
        if (lane == 0) Pp[640] = k2048 * unscale;
    }
    TSTAMPK(7, 0);
    __syncthreads();
    TSTAMPK(9, 0);
    const float* Kp = reinterpret_cast<const float*>(tab);
    auto ksum = [&](int i) -> float { return (Kp[i] + Kp[3584 + i]) + Kp[7168 + i]; };
    auto ksum4 = [&](int q) -> float4 {
        const float4 a = reinterpret_cast<const float4*>(Kp)[q], b = reinterpret_cast<const float4*>(Kp)[896 + q], c = reinterpret_cast<const float4*>(Kp)[1792 + q];
        return make_float4((a.x + b.x) + c.x, (a.y + b.y) + c.y, (a.z + b.z) + c.z, (a.w + b.w) + c.w);
    };
    uint32_t* E2w = reinterpret_cast<uint32_t*>(E);
    {
        float4 v = ksum4(tid);
        if (tid == 95) v.w -= rbf(ksum(384));
        const uint32_t lo = pack2(v.x, v.y), hi = pack2(v.z, v.w);
        if (tid < 64) { E2w[9 + 2 * tid] = lo; E2w[10 + 2 * tid] = hi; }
        else {
            const int l = 256 + 8 * (tid - 64);
            if (tid > 64) E[18 + l - 1] = (unsigned short)lo;
            E2w[9 + l / 2] = __byte_perm(lo, 0, 0x1010);
            E2w[10 + l / 2] = __byte_perm(lo, hi, 0x5432);
            E2w[11 + l / 2] = __byte_perm(hi, 0, 0x1010);
            E[18 + l + 6] = (unsigned short)(hi >> 16);
        }
    }
    if (tid < 64) {
        float4 v = ksum4(96 + tid);
        if (tid == 31) v.w -= rbf(ksum(512));
        const int o = (tid < 32 ? 317 : 417 - 64) + 2 * tid;
        E2w[o] = pack2(v.x, v.y); E2w[o + 1] = pack2(v.z, v.w);
    } else if (tid == 88) E[800 + 34 + 128] = (unsigned short)(__float_as_uint(rbf(ksum(640))) >> 16);
    if (job < 1600) {
        const int c = lane & 7, n = sn & 0xffff;
#pragma unroll
        for (int q = 0; q < 4; q++) {
            uint32_t w[4];
#pragma unroll
            for (int j = 0; j < 4; j++) w[j] = __byte_perm(sw[4 * j + (q >> 1)], sw[4 * j + 2 + (q >> 1)], (q & 1) ? 0x7632 : 0x5410);
            *reinterpret_cast<uint4*>(sdst + (n + q) * 128 + ((c ^ ((n + q) & 7)) << 4)) = make_uint4(w[0], w[1], w[2], w[3]);
        }
    }
    __syncthreads();
    g_tap[d * 128 + tid] = reinterpret_cast<const uint4*>(E)[tid];
    if (tid < 32) g_tap[d * 128 + 96 + tid] = reinterpret_cast<const uint4*>(E)[96 + tid];
    TSTAMPK(10, 0);
    if (isq) {
        float4 a = make_float4(0.f, 0.f, 0.f, 0.f);
#pragma unroll
        for (int i = 0; i < 8; i++) {
            a.x += __uint_as_float(sw[2 * i] << 16); a.y += __uint_as_float(sw[2 * i] & 0xffff0000u);
            a.z += __uint_as_float(sw[2 * i + 1] << 16); a.w += __uint_as_float(sw[2 * i + 1] & 0xffff0000u);
        }
#pragma unroll
        for (int o = 1; o <= 4; o <<= 1) {
            a.x += __shfl_xor_sync(~0u, a.x, o); a.y += __shfl_xor_sync(~0u, a.y, o);
            a.z += __shfl_xor_sync(~0u, a.z, o); a.w += __shfl_xor_sync(~0u, a.w, o);
        }
        if ((lane & 7) == 0) *reinterpret_cast<float4*>(g_csp + (sn >> 16) * 1920 + (sn & 0xffff)) = a;
    }
    TSTAMPK(11, 0);
    SPAN(0, 3);
}

#define CV_MODE 0
#define CV_SLEEP 100
constexpr int CV_CPB = 5;
constexpr int CV_THREADS = 512;
constexpr int UPADF = 128;
constexpr int ULEN = UPADF + SEQ + 80;
constexpr int XLEN = SEQ + 16;
constexpr int BX_5 = 0, BX_3 = 3264, BX_9 = 6528, BX_7 = 8960, BX_LEN = 11392;
constexpr int CV_SM_T = 0;
constexpr int CV_SM_B = CV_CPB * TAPB;
constexpr int CV_SM_U = CV_SM_B + CV_CPB * BX_LEN;
constexpr int CV_SM_X = CV_SM_U + CV_CPB * ULEN * 2;
constexpr int CV_SM_Y = CV_SM_X + CV_CPB * XLEN * 2;
constexpr int CV_SM_P = CV_SM_Y + CV_CPB * XLEN * 2;
constexpr int CV_SM_CNT = CV_SM_P + 6 * 4096;
constexpr int CV_SM_O = (CV_SM_CNT + 128 + 127) & ~127;
constexpr int CV_SMEM = CV_SM_O + 20480;
static_assert(CV_SM_B % 128 == 0 && CV_SM_CNT % 16 == 0, "layout");

__device__ __forceinline__ void mma_bf16(float* d, uint32_t a0, uint32_t a1, uint32_t a2, uint32_t a3, uint32_t b0, uint32_t b1) {
    asm volatile("mma.sync.aligned.m16n8k16.row.col.f32.bf16.bf16.f32 {%0,%1,%2,%3}, {%4,%5,%6,%7}, {%8,%9}, {%0,%1,%2,%3};"
                 : "+f"(d[0]), "+f"(d[1]), "+f"(d[2]), "+f"(d[3]) : "r"(a0), "r"(a1), "r"(a2), "r"(a3), "r"(b0), "r"(b1));
}
__device__ __forceinline__ void mma_bf16_k8(float* d, uint32_t a0, uint32_t a1, uint32_t b0) {
    asm volatile("mma.sync.aligned.m16n8k8.row.col.f32.bf16.bf16.f32 {%0,%1,%2,%3}, {%4,%5}, {%6}, {%0,%1,%2,%3};"
                 : "+f"(d[0]), "+f"(d[1]), "+f"(d[2]), "+f"(d[3]) : "r"(a0), "r"(a1), "r"(b0));
}
__device__ __forceinline__ void ldsm_x4(uint32_t* r, uint32_t addr) {
    asm volatile("ldmatrix.sync.aligned.m8n8.x4.shared.b16 {%0,%1,%2,%3}, [%4];"
                 : "=r"(r[0]), "=r"(r[1]), "=r"(r[2]), "=r"(r[3]) : "r"(addr));
}

__device__ __forceinline__ void ldsm_x4_t(uint32_t* r, uint32_t addr) {
    asm volatile("ldmatrix.sync.aligned.m8n8.x4.trans.shared.b16 {%0,%1,%2,%3}, [%4];"
                 : "=r"(r[0]), "=r"(r[1]), "=r"(r[2]), "=r"(r[3]) : "r"(addr));
}
__device__ __forceinline__ uint32_t ln2(uint32_t x, uint32_t m, float ra, float rb) {
    const __nv_bfloat162 d = __hsub2(*reinterpret_cast<const __nv_bfloat162*>(&x), *reinterpret_cast<const __nv_bfloat162*>(&m));
    const uint32_t w = *reinterpret_cast<const uint32_t*>(&d);
    return pack2(__uint_as_float(w << 16) * ra, __uint_as_float(w & 0xffff0000u) * rb);
}
__device__ __forceinline__ void cp_async16(uint32_t dst, const void* src) {
    asm volatile("cp.async.cg.shared.global [%0], [%1], 16;" ::"r"(dst), "l"(src));
}
__device__ __forceinline__ void cp_async_wait_all() { asm volatile("cp.async.wait_all;" ::: "memory"); }

template <bool FULL>
__device__ __forceinline__ void direct_pass(float (&acc)[8][4], uint32_t ub, uint32_t o0, uint32_t o1, const uint2* __restrict__ Tp, bool first_half) {
    uint32_t sw[8][8];
#pragma unroll
    for (int j = 0; j < 8; j++) { ldsm_x4(&sw[j][0], ub + o0 + j * 256); ldsm_x4(&sw[j][4], ub + o1 + j * 256); }
#pragma unroll
    for (int M = 0; M < 4; M++) {
#pragma unroll
        for (int i = 0; i < 4; i++) {
            const uint2 hi = Tp[128 * M + 16 * i], lo = Tp[128 * M + 16 * i - 8];
#pragma unroll
            for (int j = FULL ? 0 : M; j < 8; j++) mma_bf16(acc[j], hi.x, hi.y, lo.x, lo.y, sw[(j - M) & 7][2 * i], sw[(j - M) & 7][2 * i + 1]);
        }
        if (FULL) {
            ldsm_x4(&sw[7 - M][0], ub + o0 - (M + 1) * 256);
            if (M < 3) ldsm_x4(&sw[7 - M][4], ub + o1 - (M + 1) * 256);
        }
    }
    if (first_half) {
        const uint2 hi = Tp[512], lo = Tp[504];
#pragma unroll
        for (int j = FULL ? 0 : 4; j < 8; j++) mma_bf16(acc[j], hi.x, hi.y, lo.x, lo.y, sw[(j - 4) & 7][0], sw[(j - 4) & 7][1]);
    }
}
__device__ __forceinline__ void mbar_init(uint32_t bar, int count) { asm volatile("mbarrier.init.shared::cta.b64 [%0], %1;" ::"r"(bar), "r"(count)); }
__device__ __forceinline__ void mbar_arrive(uint32_t bar) { asm volatile("mbarrier.arrive.shared::cta.b64 _, [%0];" ::"r"(bar) : "memory"); }
__device__ __forceinline__ void mbar_wait(uint32_t bar, uint32_t parity) {
    asm volatile("{\n.reg .pred p;\nWAIT_LOOP:\n"
                 "mbarrier.try_wait.parity.shared::cta.b64 p, [%0], %1;\n"
                 "@p bra.uni WAIT_DONE;\nbra.uni WAIT_LOOP;\nWAIT_DONE:\n}" ::"r"(bar), "r"(parity) : "memory");
}

__device__ __forceinline__ void mbar_expect_tx(uint32_t bar, uint32_t bytes) {
    asm volatile("mbarrier.arrive.expect_tx.shared::cta.b64 _, [%0], %1;" ::"r"(bar), "r"(bytes) : "memory");
}
__device__ __forceinline__ void tma_load_2d(uint32_t dst, const void* tmap, int c0, int c1, uint32_t bar) {
    asm volatile("cp.async.bulk.tensor.2d.shared::cluster.global.mbarrier::complete_tx::bytes [%0], [%1, {%3, %4}], [%2];"
                 ::"r"(dst), "l"(tmap), "r"(bar), "r"(c0), "r"(c1) : "memory");
}
__device__ __forceinline__ void fence_async_smem() { asm volatile("fence.proxy.async.shared::cta;" ::: "memory"); }
__device__ __forceinline__ void bulk_load(uint32_t dst, const void* src, uint32_t bytes, uint32_t bar) {
    asm volatile("cp.async.bulk.shared::cluster.global.mbarrier::complete_tx::bytes [%0], [%1], %2, [%3];"
                 ::"r"(dst), "l"(src), "r"(bytes), "r"(bar) : "memory");
}
__device__ __forceinline__ void tma_store_2d(const void* tmap, int c0, int c1, uint32_t src) {
    asm volatile("cp.async.bulk.tensor.2d.global.shared::cta.bulk_group [%0, {%1, %2}], [%3];" ::"l"(tmap), "r"(c0), "r"(c1), "r"(src) : "memory");
    asm volatile("cp.async.bulk.commit_group;" ::: "memory");
    asm volatile("cp.async.bulk.wait_group.read 0;" ::: "memory");
}
__device__ __forceinline__ void stsm_x4(uint32_t addr, uint32_t r0, uint32_t r1, uint32_t r2, uint32_t r3) {
    asm volatile("stmatrix.sync.aligned.m8n8.x4.shared.b16 [%0], {%1,%2,%3,%4};" ::"r"(addr), "r"(r0), "r"(r1), "r"(r2), "r"(r3) : "memory");
}
__device__ __forceinline__ void stsm_x4_t(uint32_t addr, uint32_t r0, uint32_t r1, uint32_t r2, uint32_t r3) {
    asm volatile("stmatrix.sync.aligned.m8n8.x4.trans.shared.b16 [%0], {%1,%2,%3,%4};" ::"r"(addr), "r"(r0), "r"(r1), "r"(r2), "r"(r3) : "memory");
}
__device__ __forceinline__ void prefetch_tmap(const void* tmap) { asm volatile("prefetch.tensormap [%0];" ::"l"(tmap) : "memory"); }

__device__ __forceinline__ uint32_t fin2(uint32_t x, uint32_t y, uint32_t u, uint32_t dk) {
    typedef __nv_bfloat162 b2;
    const b2 r = __hadd2_rn(*reinterpret_cast<const b2*>(&x), __hadd2_rn(*reinterpret_cast<const b2*>(&y),
                            __hmul2_rn(*reinterpret_cast<const b2*>(&u), *reinterpret_cast<const b2*>(&dk))));
    return *reinterpret_cast<const uint32_t*>(&r);
}
__global__ void __launch_bounds__(CV_THREADS, 1) conv_kernel(const bf16* __restrict__ Dskip, int layer, const __grid_constant__ CUtensorMap tmOut) {
    extern __shared__ __align__(128) unsigned char sm[];
    SPAN(3 + 4 * layer, 0);
    bf16* Us = reinterpret_cast<bf16*>(sm + CV_SM_U);
    bf16* Xs = reinterpret_cast<bf16*>(sm + CV_SM_X);
    bf16* Ys = reinterpret_cast<bf16*>(sm + CV_SM_Y);
    const int tid = threadIdx.x, lane = tid & 31, warp = __shfl_sync(~0u, tid >> 5, 0);
    const int d0 = blockIdx.x * CV_CPB, tile = blockIdx.x; (void)tile;
    TSTAMP1X(9, 256);
    unsigned short dskr;
    asm volatile("ld.global.nc.u16 %0, [%1];" : "=h"(dskr) : "l"(Dskip + d0 + min(lane, CV_CPB - 1)));
    if (tid >= 256) {
        const int t2 = tid - 256;
        if (t2 == 0) {
            mbar_init(smem_u32(sm + CV_SM_CNT) + 104, 1);
            asm volatile("fence.mbarrier_init.release.cluster;" ::: "memory");
            mbar_expect_tx(smem_u32(sm + CV_SM_CNT) + 104, CV_CPB * 2048);
            bulk_load(smem_u32(sm + CV_SM_O), g_tap + d0 * 128, CV_CPB * 2048, smem_u32(sm + CV_SM_CNT) + 104);
        } else if (lane == 0) {
            mbar_init(smem_u32(sm + CV_SM_CNT) + 16 * (warp - 9), warp == 15 ? 16 : 1);
            if (warp < 15) mbar_init(smem_u32(sm + CV_SM_CNT) + 16 * (warp - 9) + 8, 1);
            else if (layer) prefetch_tmap(&tmOut);
        }
        if (t2 < 149) {
            const int k = t2;
            const int off = k < 18 ? BX_5 + 8 * k : k < 37 ? BX_3 + 8 * (k - 18) : k < 69 ? BX_9 + 8 * (k - 37) : k < 101 ? BX_7 + 8 * (k - 69)
                          : k < 133 ? 8 * (k - 101) : (UPADF + SEQ) * 2 + 8 * (k - 133);
#pragma unroll
            for (int c = 0; c < CV_CPB; c++) *reinterpret_cast<uint2*>(sm + (k < 101 ? CV_SM_B + c * BX_LEN : CV_SM_U + c * ULEN * 2) + off) = make_uint2(0, 0);
        }
        asm volatile("bar.sync 1, 256;" ::: "memory");
        TSTAMP1X(10, 256);
        mbar_wait(smem_u32(sm + CV_SM_CNT) + 104, 0);
        TSTAMP1X(11, 256);
#pragma unroll 1
        for (int r = t2; r < 392; r += 256) {
            const bool dd = r < 272, cc = r >= 368;
            const uint32_t* E2 = reinterpret_cast<const uint32_t*>(sm + CV_SM_O) + (dd ? r : r < 320 ? 300 + 2 * (r - 272) : cc ? 416 : 400 + 2 * (r - 320));
            const uint32_t* E3 = E2 + (dd ? 4 : cc ? 0 : 1);
            const uint32_t s0 = !cc ? 0x7610u : r == 382 ? 0x1044u : 0x4444u, s1 = !cc ? 0x7610u : r == 378 ? 0x1044u : 0x4444u;
            const uint32_t s2 = !cc ? 0x1032u : r == 381 ? 0x4410u : 0x4444u, s3 = !cc ? 0x1032u : r == 377 ? 0x4410u : 0x4444u;
            uint32_t w[CV_CPB][4];
#pragma unroll
            for (int c = 0; c < CV_CPB; c++) { w[c][0] = E2[512 * c]; w[c][1] = E2[512 * c + 1]; w[c][2] = E3[512 * c]; w[c][3] = E3[512 * c + 1]; }
#pragma unroll
            for (int c = 0; c < CV_CPB; c++) {
                const uint32_t a = __byte_perm(w[c][3], w[c][2], s1), b = __byte_perm(w[c][1], w[c][0], s2);
                *reinterpret_cast<uint4*>(sm + CV_SM_T + c * TAPB + r * 16) =
                    make_uint4(__byte_perm(w[c][1], w[c][0], s0), dd || cc ? a : b, dd || cc ? b : a, __byte_perm(w[c][3], w[c][2], s3));
            }
        }
        TSTAMP1X(12, 256);
        if (layer == 0) {
#pragma unroll
            for (int c = 0; c < CV_CPB; c++) reinterpret_cast<uint4*>(g_yT + (size_t)(d0 + c) * XCP)[t2] = make_uint4(~0u, ~0u, ~0u, ~0u);
        }
        pdl_sync();
        if (layer && blockIdx.x == 0 && t2 == 0) g_epoch = ld_epoch();
    } else {
        const uint4* ppv = reinterpret_cast<const uint4*>(g_piv + layer * SEQ) + tid;
        const float4* psv = reinterpret_cast<const float4*>(g_sum + layer * SEQ) + tid;
        const uint4* pxv = reinterpret_cast<const uint4*>(g_x1T + (size_t)d0 * XCP) + tid;
        asm volatile("" : "+l"(ppv), "+l"(psv), "+l"(pxv));
        pdl_sync();
        SPAN(3 + 4 * layer, 1);
        TSTAMP(0);
        if (threadIdx.x == 0) { GSTAMP(g_tim, 15); }
        float4 sv[4];
#pragma unroll
        for (int k = 0; k < 4; k++) sv[k] = __ldcg(psv + 256 * k);
        const uint4 pv = __ldcg(ppv);
        uint4 xv[CV_CPB];
#pragma unroll
        for (int c = 0; c < CV_CPB; c++) xv[c] = __ldcg(pxv + c * (XCP / 8));
        uint32_t mw[4];
        float rs[8];
#pragma unroll
        for (int k = 0; k < 4; k++) {
            const uint32_t pw = k == 0 ? pv.x : k == 1 ? pv.y : k == 2 ? pv.z : pv.w;
            const float d0_ = sv[k].x * (1.0f / DM), d1_ = sv[k].z * (1.0f / DM);
            mw[k] = pack2(__uint_as_float(pw << 16) + d0_, __uint_as_float(pw & 0xffff0000u) + d1_);
            const uint32_t vr = pack2(fmaxf(fmaf(-d0_, d0_, sv[k].y * (1.0f / DM)), 0.f), fmaxf(fmaf(-d1_, d1_, sv[k].w * (1.0f / DM)), 0.f));
            const uint32_t ve = pack2(__uint_as_float(vr << 16) + 1e-5f, __uint_as_float(vr & 0xffff0000u) + 1e-5f);
            const uint32_t sd = pack2(sqrt_apx(__uint_as_float(ve << 16)), sqrt_apx(__uint_as_float(ve & 0xffff0000u)));
            rs[2 * k] = rcp_apx(__uint_as_float(sd << 16)); rs[2 * k + 1] = rcp_apx(__uint_as_float(sd & 0xffff0000u));
        }
        if (rs[0] != 123.f) TSTAMP(13);
        const int ch = tid + UPADF / 8, pch = ch ^ ((ch >> 3) & 1);
#pragma unroll
        for (int c = 0; c < CV_CPB; c++) {
            *reinterpret_cast<uint4*>(Xs + c * XLEN + tid * 8) = xv[c];
            *reinterpret_cast<uint4*>(Us + c * ULEN + pch * 8) =
                make_uint4(ln2(xv[c].x, mw[0], rs[0], rs[1]), ln2(xv[c].y, mw[1], rs[2], rs[3]), ln2(xv[c].z, mw[2], rs[4], rs[5]), ln2(xv[c].w, mw[3], rs[6], rs[7]));
        }
    }
    __syncthreads();
    TSTAMP(1);
    const uint32_t rstart = warp < 8 ? (warp < 4 ? 0x02000000u : 0x06040000u) : (warp < 12 ? 0x0C0B0A08u : 0x1E1D150Fu);
    const uint32_t rcount = warp < 8 ? 0x02020000u : (warp < 12 ? 0x03010102u : 0x01010806u);
#pragma unroll 1
    for (int rd = (rstart >> (8 * (warp & 3))) & 0xff, re = rd + ((rcount >> (8 * (warp & 3))) & 0xff); rd < re; rd++) {
        const int i = 32 * rd + lane;
        if (i < CV_CPB * 193) {
            const int c = i / 193, chunk = i - c * 193 - 1, ch = chunk + UPADF / 8;
            const bf16* uc = Us + c * ULEN;
            const uint4 o = *reinterpret_cast<const uint4*>(uc + (ch ^ ((ch >> 3) & 1)) * 8);
            const uint2 lo = *reinterpret_cast<const uint2*>(uc + ((ch - 1) ^ (((ch - 1) >> 3) & 1)) * 8 + 4);
            const uint2 hi = *reinterpret_cast<const uint2*>(uc + ((ch + 1) ^ (((ch + 1) >> 3) & 1)) * 8);
            const uint32_t w[8] = {lo.x, lo.y, o.x, o.y, o.z, o.w, hi.x, hi.y};
            float v[16], b[8];
#pragma unroll
            for (int k = 0; k < 8; k++) { v[2 * k] = __uint_as_float(w[k] << 16); v[2 * k + 1] = __uint_as_float(w[k] & 0xffff0000u); }
            unsigned char* bx = sm + CV_SM_B + c * BX_LEN + chunk * 16;
#pragma unroll
            for (int k = 0; k < 8; k++) b[k] = v[k + 4] + (v[k + 3] + v[k + 5]);
            *reinterpret_cast<uint2*>(bx + BX_3 + 168) = make_uint2(pack2(b[0], b[1]), pack2(b[2], b[3]));
            *reinterpret_cast<uint2*>(bx + BX_3 + 176) = make_uint2(pack2(b[4], b[5]), pack2(b[6], b[7]));
#pragma unroll
            for (int k = 0; k < 8; k++) b[k] += v[k + 2] + v[k + 6];
            *reinterpret_cast<uint4*>(bx + BX_5 + 160) = make_uint4(pack2(b[0], b[1]), pack2(b[2], b[3]), pack2(b[4], b[5]), pack2(b[6], b[7]));
            if (chunk < 128) {
#pragma unroll
                for (int k = 0; k < 8; k++) b[k] += v[k + 1] + v[k + 7];
                *reinterpret_cast<uint4*>(bx + BX_7 + 272) = make_uint4(pack2(b[0], b[1]), pack2(b[2], b[3]), pack2(b[4], b[5]), pack2(b[6], b[7]));
#pragma unroll
                for (int k = 0; k < 8; k++) b[k] += v[k] + v[k + 8];
                *reinterpret_cast<uint4*>(bx + BX_9 + 272) = make_uint4(pack2(b[0], b[1]), pack2(b[2], b[3]), pack2(b[4], b[5]), pack2(b[6], b[7]));
            }
        }
    }
    __syncwarp();
    if (lane == 0) mbar_arrive(smem_u32(sm + CV_SM_CNT) + 96);
    TSTAMP(2);
    {
        const int g = lane >> 2, ti = lane & 3;
        const int e = g - 2 * ti;
        uint32_t lds_off[4];
        uint32_t off2, off3, offc;
        {
            const int mat = lane >> 3, r = lane & 7;
#pragma unroll
            for (int pr = 0; pr < 4; pr++) {
                const int iw = 2 * pr + (mat >> 1), half = mat & 1;
                const int chunk = (UPADF - 16 * iw + 16 * r + 8 * half) >> 3;
                lds_off[pr] = (uint32_t)((chunk ^ ((chunk >> 3) & 1)) * 16);
            }
            const int j2 = 13 + r + 8 * (mat >> 1), j3 = j2 + 2, i0 = 8 * (mat & 1);
            off2 = (j2 & 1) ? BX_3 + (4 * j2 + i0 + 84) * 2 : BX_5 + (4 * j2 + i0 + 80) * 2;
            off3 = ((j3 & 1) ? BX_7 : BX_9) + (8 * j3 + i0 + 136) * 2;
            const int cc = (UPADF + 16 * (r + (mat >> 1)) + i0) >> 3;
            offc = (uint32_t)((cc ^ ((cc >> 3) & 1)) * 16);
        }
        const uint32_t rtab = warp < 8 ? (warp < 4 ? 0x0B090200u : 0x0C0A0301u) : (warp < 12 ? 0x13111008u : 0x1412241Cu);
        const int rl = (rtab >> (8 * (warp & 3))) & 0xff, type = rl >> 3, c = rl & 7;
        const int H = (type == 1 || type == 2) ? 1 : 0, T0 = 8 * H;
        const uint2* Tc = reinterpret_cast<const uint2*>(sm + CV_SM_T + c * TAPB) + TPAD + e;
        const uint32_t ubase = smem_u32(Us + c * ULEN);
        const uint32_t bbase = smem_u32(sm + CV_SM_B + c * BX_LEN);
        float acc[8][4];
#pragma unroll
        for (int j = 0; j < 8; j++)
#pragma unroll
            for (int k = 0; k < 4; k++) acc[j][k] = 0.f;
#pragma unroll 1
        for (int pass = (type == 2 || type == 4) ? 1 : 0; pass < ((type == 1 || type == 3) ? 1 : 2); pass++) {
            const uint32_t o0 = pass ? lds_off[2] : lds_off[0], o1 = pass ? lds_off[3] : lds_off[1];
            if (H) direct_pass<true>(acc, ubase + T0 * 256, o0, o1, Tc + 64 * pass, pass == 0);
            else direct_pass<false>(acc, ubase, o0, o1, Tc + 64 * pass, pass == 0);
        }
        TSTAMP(6);
        mbar_wait(smem_u32(sm + CV_SM_CNT) + 96, 0);
        if (type != 1 && type != 4) {
            const uint32_t* w2 = reinterpret_cast<const uint32_t*>(sm + CV_SM_T + c * TAPB + TAP_W2) + (115 - 96) + 4 * g - 2 * ti;
            uint32_t f[10][2];
#pragma unroll
            for (int k = 0; k < 10; k++) { f[k][0] = w2[16 * k]; f[k][1] = w2[16 * k - 8]; }
            const uint32_t ab = bbase + off2 + (2 * T0 + 6) * 128;
            const int kmax = H ? 23 : 8;
            uint32_t a[3][4];
            ldsm_x4_t(a[0], ab);
            ldsm_x4_t(a[1], ab - 128);
#pragma unroll
            for (int kp = 0; kp < 24; kp++) {
                if (kp > kmax) break;
                if (kp < 22) ldsm_x4_t(a[(kp + 2) % 3], ab - min(kp + 2, kmax) * 128);
#pragma unroll
                for (int j = 0; j < 8; j++) {
                    const int ee = 2 * j - 14 + kp;
                    if (ee >= 0 && ee <= 9) mma_bf16(acc[j], a[kp % 3][0], a[kp % 3][1], a[kp % 3][2], a[kp % 3][3], f[ee][0], f[ee][1]);
                }
            }
        }
        TSTAMP(7);
        if (type != 2 && type != 4) {
            const uint32_t* w3 = reinterpret_cast<const uint32_t*>(sm + CV_SM_T + c * TAPB + TAP_W3) + (129 - 96) + 2 * (g - ti);
            uint32_t f[9][2];
#pragma unroll
            for (int k = 0; k < 9; k++) { f[k][0] = w3[16 * k]; f[k][1] = w3[16 * k - 8]; }
            const uint32_t ab = bbase + off3 + (T0 - 2) * 256;
            uint32_t a[3][4];
            ldsm_x4_t(a[0], ab);
            ldsm_x4_t(a[1], ab - H * 256);
#pragma unroll
            for (int kp = 0; kp < 9; kp++) {
                if (kp > T0) break;
                if (kp < 7) ldsm_x4_t(a[(kp + 2) % 3], ab - min(kp + 2, T0) * 256);
#pragma unroll
                for (int j = 0; j < 8; j++) {
                    const int dl = j - 7 + kp;
                    if (dl >= 0 && dl <= 8) mma_bf16(acc[j], a[kp % 3][0], a[kp % 3][1], a[kp % 3][2], a[kp % 3][3], f[dl][0], f[dl][1]);
                }
            }
            const uint2* Dc = reinterpret_cast<const uint2*>(sm + CV_SM_T + c * TAPB + TAP_C) + e;
            const uint2 h63 = Dc[16], h64 = Dc[32], l63 = Dc[8], l64 = Dc[24];
#pragma unroll
            for (int j = 0; j < 8; j++)
                if (j == 7 || H) {
                    uint32_t bq[4];
                    ldsm_x4(bq, ubase + offc + (T0 + j - 8) * 256);
                    mma_bf16(acc[j], h64.x, h64.y, l64.x, l64.y, bq[0], bq[1]);
                    mma_bf16(acc[j], h63.x, h63.y, l63.x, l63.y, bq[2], bq[3]);
                }
        }
        TSTAMP(8);
        const bool hi_half = (type == 2 || type == 4);
        if (type != 0) {
            const int pair = H ? c : 5;
            float4* give = reinterpret_cast<float4*>(sm + CV_SM_P + pair * 4096 + (hi_half ? 2048 : 0)) + lane;
            const float4* take = reinterpret_cast<const float4*>(sm + CV_SM_P + pair * 4096 + (hi_half ? 0 : 2048)) + lane;
            const uint32_t pb = smem_u32(sm + CV_SM_CNT) + pair * 16;
#pragma unroll
            for (int j = 0; j < 4; j++)
                give[32 * j] = hi_half ? make_float4(acc[j][0], acc[j][1], acc[j][2], acc[j][3]) : make_float4(acc[j + 4][0], acc[j + 4][1], acc[j + 4][2], acc[j + 4][3]);
            __syncwarp();
            if (lane == 0) mbar_arrive(pb + (hi_half ? 8 : 0));
            mbar_wait(pb + (hi_half ? 0 : 8), 0);
#pragma unroll
            for (int j = 0; j < 4; j++) {
                const float4 v = take[32 * j];
                acc[j][0] = (hi_half ? acc[j + 4][0] : acc[j][0]) + v.x; acc[j][1] = (hi_half ? acc[j + 4][1] : acc[j][1]) + v.y;
                acc[j][2] = (hi_half ? acc[j + 4][2] : acc[j][2]) + v.z; acc[j][3] = (hi_half ? acc[j + 4][3] : acc[j][3]) + v.w;
            }
        }
        const uint32_t dk = __shfl_sync(~0u, (uint32_t)dskr, c) * 0x10001u;
#pragma unroll 1
        for (int rnd = 0; rnd < (type == 0 ? 2 : 1); rnd++) {
            const int Q = 2 * H + (hi_half ? 1 : rnd);
            if (rnd) {
#pragma unroll
                for (int j = 0; j < 4; j++)
#pragma unroll
                    for (int k = 0; k < 4; k++) acc[j][k] = acc[j + 4][k];
            }
            const uint32_t ya = smem_u32(Ys + c * XLEN) + (128 * (4 * Q + (lane >> 4)) + 16 * (lane & 7) + 8 * ((lane >> 3) & 1)) * 2;
#pragma unroll
            for (int j = 0; j < 4; j += 2)
                asm volatile("stmatrix.sync.aligned.m8n8.x4.trans.shared.b16 [%0], {%1,%2,%3,%4};" ::"r"(ya + j * 256),
                             "r"(pack2(acc[j][0], acc[j][1])), "r"(pack2(acc[j][2], acc[j][3])),
                             "r"(pack2(acc[j + 1][0], acc[j + 1][1])), "r"(pack2(acc[j + 1][2], acc[j + 1][3])) : "memory");
            __syncwarp();
            uint4 yv[2], xv[2], uv[2];
#pragma unroll
            for (int k = 0; k < 2; k++) {
                const int t = 512 * Q + 256 * k + 8 * lane, cu = (t + UPADF) >> 3;
                yv[k] = *reinterpret_cast<const uint4*>(Ys + c * XLEN + t);
                xv[k] = *reinterpret_cast<const uint4*>(Xs + c * XLEN + t);
                uv[k] = *reinterpret_cast<const uint4*>(Us + c * ULEN + (cu ^ ((cu >> 3) & 1)) * 8);
            }
#pragma unroll
            for (int k = 0; k < 2; k++)
                asm volatile("st.relaxed.gpu.global.v4.u32 [%0], {%1,%2,%3,%4};" ::"l"((layer ? g_yT : g_xcT) + (size_t)(d0 + c) * XCP + 512 * Q + 256 * k + 8 * lane),
                             "r"(fin2(xv[k].x, yv[k].x, uv[k].x, dk)), "r"(fin2(xv[k].y, yv[k].y, uv[k].y, dk)), "r"(fin2(xv[k].z, yv[k].z, uv[k].z, dk)), "r"(fin2(xv[k].w, yv[k].w, uv[k].w, dk)) : "memory");
        }
        TSTAMP(4);
        if (layer == 1) {
            const int mb = blockIdx.x >> 3, cg = blockIdx.x & 7;
            const bf16* src = g_yT + (size_t)(cg * 80 + (tid >> 4)) * XCP + mb * 128 + (tid & 15) * 8;
            uint32_t v[3][4];
            __syncthreads();
            TSTAMP(5);
            uint32_t todo = warp < 8 ? 7 : 3;
#pragma unroll 1
            for (int it = 0; it < SPIN_MAX; it++) {
#pragma unroll
                for (int k = 0; k < 3; k++)
                    if (todo >> k & 1)
                        asm volatile("ld.relaxed.gpu.global.v4.u32 {%0,%1,%2,%3}, [%4];" : "=r"(v[k][0]), "=r"(v[k][1]), "=r"(v[k][2]), "=r"(v[k][3]) : "l"(src + k * (32 * XCP)) : "memory");
#pragma unroll
                for (int k = 0; k < 3; k++)
                    if ((todo >> k & 1) && v[k][0] != ~0u && v[k][1] != ~0u && v[k][2] != ~0u && v[k][3] != ~0u) {
                        *reinterpret_cast<uint4*>(sm + (32 * k + (tid >> 4)) * 272 + (tid & 15) * 16) = make_uint4(v[k][0], v[k][1], v[k][2], v[k][3]);
                        todo ^= 1u << k;
                    }
                if (!todo) break;
                __nanosleep(CV_SLEEP);
            }
            __syncthreads();
            uint32_t w[12];
#pragma unroll
            for (int k = 0; k < 3; k++) ldsm_x4(&w[4 * k], smem_u32(sm) + min(32 * k + lane, 79) * 272 + warp * 16);
            const uint32_t ot = smem_u32(sm + CV_SM_O) + warp * 1280, oa = ot + (lane & 7) * 160 + (lane >> 3) * 16;
            stsm_x4_t(oa, w[0], w[1], w[2], w[3]);
            stsm_x4_t(oa + 64, w[4], w[5], w[6], w[7]);
            asm volatile("stmatrix.sync.aligned.m8n8.x2.trans.shared.b16 [%0], {%1,%2};" ::"r"(oa + 128), "r"(w[8]), "r"(w[9]) : "memory");
            fence_async_smem();
            __syncwarp();
            if (lane == 0) tma_store_2d(&tmOut, cg * 80, mb * 128 + 8 * warp, ot);
        }
    }
    TSTAMP(3);
    GSTAMP(g_tim, 14);
    SPAN(3 + 4 * layer, 3);
}

__device__ __forceinline__ void wgmma_fence() { asm volatile("wgmma.fence.sync.aligned;" ::: "memory"); }
__device__ __forceinline__ void wgmma_commit() { asm volatile("wgmma.commit_group.sync.aligned;" ::: "memory"); }
template <int N> __device__ __forceinline__ void wgmma_wait() { asm volatile("wgmma.wait_group.sync.aligned %0;" ::"n"(N) : "memory"); }
__device__ __forceinline__ uint64_t make_desc(uint32_t addr, uint32_t lbo, uint32_t sbo, uint32_t mode) {
    return (uint64_t)((addr & 0x3FFFF) >> 4) | ((uint64_t)(lbo >> 4) << 16) | ((uint64_t)(sbo >> 4) << 32) | ((uint64_t)mode << 62);
}
template <int TA, int TB>
__device__ __forceinline__ void wgmma_n240(float (&d)[120], uint64_t da, uint64_t db) {
    asm volatile("wgmma.mma_async.sync.aligned.m64n240k16.f32.bf16.bf16 {%0,%1,%2,%3,%4,%5,%6,%7,%8,%9,%10,%11,%12,%13,%14,%15,%16,%17,%18,%19,%20,%21,%22,%23,%24,%25,%26,%27,%28,%29,%30,%31,%32,%33,%34,%35,%36,%37,%38,%39,%40,%41,%42,%43,%44,%45,%46,%47,%48,%49,%50,%51,%52,%53,%54,%55,%56,%57,%58,%59,%60,%61,%62,%63,%64,%65,%66,%67,%68,%69,%70,%71,%72,%73,%74,%75,%76,%77,%78,%79,%80,%81,%82,%83,%84,%85,%86,%87,%88,%89,%90,%91,%92,%93,%94,%95,%96,%97,%98,%99,%100,%101,%102,%103,%104,%105,%106,%107,%108,%109,%110,%111,%112,%113,%114,%115,%116,%117,%118,%119}, %120, %121, 1, 1, 1, %122, %123;"
                 : "+f"(d[0]), "+f"(d[1]), "+f"(d[2]), "+f"(d[3]), "+f"(d[4]), "+f"(d[5]), "+f"(d[6]), "+f"(d[7]), "+f"(d[8]), "+f"(d[9]), "+f"(d[10]), "+f"(d[11]), "+f"(d[12]), "+f"(d[13]), "+f"(d[14]), "+f"(d[15]), "+f"(d[16]), "+f"(d[17]), "+f"(d[18]), "+f"(d[19]), "+f"(d[20]), "+f"(d[21]), "+f"(d[22]), "+f"(d[23]), "+f"(d[24]), "+f"(d[25]), "+f"(d[26]), "+f"(d[27]), "+f"(d[28]), "+f"(d[29]), "+f"(d[30]), "+f"(d[31]), "+f"(d[32]), "+f"(d[33]), "+f"(d[34]), "+f"(d[35]), "+f"(d[36]), "+f"(d[37]), "+f"(d[38]), "+f"(d[39]), "+f"(d[40]), "+f"(d[41]), "+f"(d[42]), "+f"(d[43]), "+f"(d[44]), "+f"(d[45]), "+f"(d[46]), "+f"(d[47]), "+f"(d[48]), "+f"(d[49]), "+f"(d[50]), "+f"(d[51]), "+f"(d[52]), "+f"(d[53]), "+f"(d[54]), "+f"(d[55]), "+f"(d[56]), "+f"(d[57]), "+f"(d[58]), "+f"(d[59]), "+f"(d[60]), "+f"(d[61]), "+f"(d[62]), "+f"(d[63]), "+f"(d[64]), "+f"(d[65]), "+f"(d[66]), "+f"(d[67]), "+f"(d[68]), "+f"(d[69]), "+f"(d[70]), "+f"(d[71]), "+f"(d[72]), "+f"(d[73]), "+f"(d[74]), "+f"(d[75]), "+f"(d[76]), "+f"(d[77]), "+f"(d[78]), "+f"(d[79]), "+f"(d[80]), "+f"(d[81]), "+f"(d[82]), "+f"(d[83]), "+f"(d[84]), "+f"(d[85]), "+f"(d[86]), "+f"(d[87]), "+f"(d[88]), "+f"(d[89]), "+f"(d[90]), "+f"(d[91]), "+f"(d[92]), "+f"(d[93]), "+f"(d[94]), "+f"(d[95]), "+f"(d[96]), "+f"(d[97]), "+f"(d[98]), "+f"(d[99]), "+f"(d[100]), "+f"(d[101]), "+f"(d[102]), "+f"(d[103]), "+f"(d[104]), "+f"(d[105]), "+f"(d[106]), "+f"(d[107]), "+f"(d[108]), "+f"(d[109]), "+f"(d[110]), "+f"(d[111]), "+f"(d[112]), "+f"(d[113]), "+f"(d[114]), "+f"(d[115]), "+f"(d[116]), "+f"(d[117]), "+f"(d[118]), "+f"(d[119])
                 : "l"(da), "l"(db), "n"(TA), "n"(TB));
}

template <int TA, int TB>
__device__ __forceinline__ void wgmma_n80(float (&d)[40], uint64_t da, uint64_t db) {
    asm volatile("wgmma.mma_async.sync.aligned.m64n80k16.f32.bf16.bf16 {%0,%1,%2,%3,%4,%5,%6,%7,%8,%9,%10,%11,%12,%13,%14,%15,%16,%17,%18,%19,%20,%21,%22,%23,%24,%25,%26,%27,%28,%29,%30,%31,%32,%33,%34,%35,%36,%37,%38,%39}, %40, %41, 1, 1, 1, %42, %43;"
                 : "+f"(d[0]), "+f"(d[1]), "+f"(d[2]), "+f"(d[3]), "+f"(d[4]), "+f"(d[5]), "+f"(d[6]), "+f"(d[7]), "+f"(d[8]), "+f"(d[9]), "+f"(d[10]), "+f"(d[11]), "+f"(d[12]), "+f"(d[13]), "+f"(d[14]), "+f"(d[15]), "+f"(d[16]), "+f"(d[17]), "+f"(d[18]), "+f"(d[19]), "+f"(d[20]), "+f"(d[21]), "+f"(d[22]), "+f"(d[23]), "+f"(d[24]), "+f"(d[25]), "+f"(d[26]), "+f"(d[27]), "+f"(d[28]), "+f"(d[29]), "+f"(d[30]), "+f"(d[31]), "+f"(d[32]), "+f"(d[33]), "+f"(d[34]), "+f"(d[35]), "+f"(d[36]), "+f"(d[37]), "+f"(d[38]), "+f"(d[39])
                 : "l"(da), "l"(db), "n"(TA), "n"(TB));
}

constexpr int A1_THREADS = 384;
constexpr int A1_NST = 4;
#define A1_PRE0 2
#define A1_SDELAY 1
#define A1_SKEW 8
#define A1_PRE1 1
constexpr int A1_STAGE = 16384 + WQ_STAGE;
constexpr int A1_KVP = 336;
constexpr int A1_SM_KV = 2 * A1_STAGE;
constexpr int A1_SM_O = A1_SM_KV + 144 * A1_KVP;
constexpr int A1_SM_R = A1_NST * A1_STAGE;
constexpr int A1_SM_BAR = A1_SM_R + 20480;
constexpr int A1_SM_CS = A1_SM_BAR + 256;
constexpr int A1_SM_RS = A1_SM_CS + 1024;
constexpr int A1_SMEM = A1_SM_RS + 1024 + 1024;
static_assert(A1_SM_O % 128 == 0 && A1_SM_O + 20480 <= A1_SM_R, "layout");

template <int L>
__device__ __forceinline__ void a1_mainloop(float (&acc)[120], uint32_t sbase, uint32_t bars, int wg, int tile) {
    constexpr int layer = L; (void)layer;
    const uint64_t da0 = L ? make_desc(sbase + wg * 8192, 8192, 1024, 1) : make_desc(sbase + wg * 8192, 16, 1024, 1), db0 = make_desc(sbase + 16384, 16, 1024, 1);
#pragma unroll 1
    for (int t = 0; t < 10; t++) {
        const int st = t % A1_NST;
        mbar_wait(bars + 8 * st, (t / A1_NST) & 1);
        if (t == A1_SKEW && wg == 0) mbar_wait(bars + 160, 0);
        TSTAMP3(1 + t);
        wgmma_fence();
#pragma unroll
        for (int kk = 0; kk < 4; kk++) wgmma_n240<L, 0>(acc, da0 + (uint32_t)(st * (A1_STAGE / 16) + kk * (L ? 128 : 2)), db0 + (uint32_t)(st * (A1_STAGE / 16) + kk * 2));
        wgmma_commit();
        if (t == 9 && threadIdx.x == 128) { mbar_arrive(bars + 160); mbar_arrive(bars + 144); }
        if (t == A1_SKEW - 1 && wg == 0) wgmma_wait<0>(); else wgmma_wait<1>();
        if (t > 0 && t < 9 && (threadIdx.x & 127) == 0) {
            if (t != A1_SKEW || wg) mbar_arrive(bars + 8 * (A1_NST + (t - 1) % A1_NST));
            if (t == A1_SKEW - 1 && wg == 0) mbar_arrive(bars + 8 * (A1_NST + t % A1_NST));
        }
    }
}

__global__ void __launch_bounds__(A1_THREADS, 1) a1_kernel(const int layer, const bf16* __restrict__ x0, const __grid_constant__ CUtensorMap tmX,
                                                           const __grid_constant__ CUtensorMap tmR, const __grid_constant__ CUtensorMap tmOst) {
    extern __shared__ unsigned char smraw[];
    const uint32_t sbase = (smem_u32(smraw) + 1023) & ~1023u;
    const uint32_t bars = sbase + A1_SM_BAR;
    const uint32_t bar_stat = bars + 64, bar_kv = bars + 72, bar_r = bars + 152;
    const int tid = threadIdx.x, w = __shfl_sync(~0u, tid >> 5, 0), wg = w >> 2;
    const int tile = sm_tile();
    if (tile >= 128) { sm_idle(2 * layer); return; }
    const int mb = (tile >> 2) & 15, hg = 4 * (tile >> 6) + (tile & 3);
    unsigned char* stg = smraw + (sbase - smem_u32(smraw));
    float* cs = reinterpret_cast<float*>(stg + A1_SM_CS);
    float2* rst = reinterpret_cast<float2*>(stg + A1_SM_RS);
    const int pre = layer ? A1_PRE1 : A1_PRE0;
    auto issue_w = [&](int kb) {
        bulk_load(sbase + (kb % A1_NST) * A1_STAGE + 16384, reinterpret_cast<const unsigned char*>(g_wq) + (hg * 10 + kb) * WQ_STAGE, WQ_STAGE, bars + 8 * (kb % A1_NST));
    };
    auto issue_x = [&](int kb) {
        const uint32_t dst = sbase + (kb % A1_NST) * A1_STAGE, full = bars + 8 * (kb % A1_NST);
        if (layer == 0) tma_load_2d(dst, &tmX, kb * 64, mb * 128, full);
        else { tma_load_2d(dst, &tmX, mb * 128, kb * 64, full); tma_load_2d(dst + 8192, &tmX, mb * 128 + 64, kb * 64, full); }
    };
    if (w == 8) {
        if (tid == 256) {
            prefetch_tmap(&tmX);
#pragma unroll
            for (int i = 0; i < A1_NST; i++) { mbar_init(bars + 8 * i, 1); mbar_init(bars + 8 * (A1_NST + i), 2); }
            mbar_init(bar_r, 1);
            asm volatile("fence.mbarrier_init.release.cluster;" ::: "memory");
#pragma unroll
            for (int i = 0; i < A1_NST; i++) mbar_expect_tx(bars + 8 * i, A1_STAGE);
            mbar_expect_tx(bar_r, 20480);
        }
        __syncwarp();
        asm volatile("bar.arrive 0, 384;" ::: "memory");
        if (tid == 256) {
#pragma unroll 1
            for (int kb = 0; kb < pre; kb++) { if (layer) issue_w(kb); else issue_x(kb); }
            pdl_sync();
#pragma unroll 1
            for (int kb = 0; kb < A1_NST; kb++) {
                if (kb == A1_SDELAY && layer) {
                    tma_load_2d(sbase + A1_SM_R, &tmR, mb * 128, hg * 80, bar_r); tma_load_2d(sbase + A1_SM_R + 10240, &tmR, mb * 128 + 64, hg * 80, bar_r);
                }
                if (kb >= pre || layer) issue_x(kb);
                if (kb >= pre || !layer) issue_w(kb);
            }
        }
    } else {
        if (tid == 0) {
            mbar_init(bar_stat, 2);
#pragma unroll
            for (int i = 0; i < 9; i++) mbar_init(bar_kv + 8 * i, i ? 1 : 4);
            mbar_init(bars + 144, 1);
            mbar_init(bars + 160, 1);
            asm volatile("fence.mbarrier_init.release.cluster;" ::: "memory");
        } else if (tid == 320) { prefetch_tmap(&tmR); prefetch_tmap(&tmOst); }
        asm volatile("bar.sync 0, 384;" ::: "memory");
    }
    SPAN(1 + 4 * layer, 0);
    const uint32_t tag = ld_epoch();
    if (tid == 352) sm_started(2 * layer);
    constexpr int on = 1;
    if (wg == 2) {
        if (w == 9) {
        } else if (w == 8) {
            if (tid == 256) {
#pragma unroll 1
                for (int kb = A1_NST; kb < 10; kb++) {
                    mbar_wait(bars + 8 * (A1_NST + kb % A1_NST), ((kb / A1_NST) - 1) & 1);
                    mbar_expect_tx(bars + 8 * (kb % A1_NST), A1_STAGE);
                    issue_x(kb); issue_w(kb);
                }
                TSTAMP1T(6, 256);
            }
            __syncwarp();
        } else {
            const int j = tid - 320;
            if (layer == 0) {
                const uint4* src = reinterpret_cast<const uint4*>(x0 + (size_t)(mb * 128 + hg * 16 + (j >> 2)) * DM);
                uint4 v[20];
#pragma unroll
                for (int k = 0; k < 20; k++) v[k] = __ldg(src + (j & 3) + 4 * k);
                const float p0 = __uint_as_float(__shfl_sync(~0u, v[0].x, j & 28) << 16);
                float s[2] = {0.f, 0.f}, q[2] = {0.f, 0.f};
#pragma unroll
                for (int k = 0; k < 20; k++) {
                    const uint32_t w[4] = {v[k].x, v[k].y, v[k].z, v[k].w};
#pragma unroll
                    for (int i = 0; i < 4; i++) {
                        const float a = __uint_as_float(w[i] << 16) - p0, b = __uint_as_float(w[i] & 0xffff0000u) - p0;
                        s[0] += a; s[1] += b; q[0] = fmaf(a, a, q[0]); q[1] = fmaf(b, b, q[1]);
                    }
                }
                float s0 = s[0] + s[1], q0 = q[0] + q[1];
#pragma unroll
                for (int o = 1; o <= 2; o <<= 1) { s0 += __shfl_xor_sync(~0u, s0, o); q0 += __shfl_xor_sync(~0u, q0, o); }
                if ((j & 3) == 0) {
                    const float d = s0 * (1.0f / DM);
                    const uint32_t ms = pack2(p0 + d, sqrt_apx(rbf(rbf(fmaxf(fmaf(-d, d, q0 * (1.0f / DM)), 0.f)) + 1e-5f)));
                    asm volatile("st.global.cg.u64 [%0], %1;" ::"l"(g_rstat + mb * 128 + hg * 16 + (j >> 2)), "l"(tagw(ms, tag)) : "memory");
                    g_piv[mb * 128 + hg * 16 + (j >> 2)] = __ushort_as_bfloat16((unsigned short)ms);
                }
                pdl_sync();
            }
            if (j < 60) {
                float4 a = make_float4(0.f, 0.f, 0.f, 0.f);
#pragma unroll
                for (int k = 0; k < 10; k++) {
                    const float4 v = __ldcg(reinterpret_cast<const float4*>(g_csp + k * 1920 + hg * 240) + j);
                    a.x += v.x; a.y += v.y; a.z += v.z; a.w += v.w;
                }
                reinterpret_cast<float4*>(cs)[j] = a;
            }
            if (layer == 0) {
                ulonglong2 v;
#pragma unroll 1
                for (int it = 0; it < SPIN_MAX; it++) {
                    v = ld_tag2(reinterpret_cast<const ulonglong2*>(g_rstat + mb * 128) + j);
                    if (tag_ok(v, tag)) break;
                    __nanosleep(100);
                }
                *reinterpret_cast<float4*>(rst + 2 * j) = make_float4(__uint_as_float((uint32_t)v.x << 16), rcp_apx(__uint_as_float((uint32_t)v.x & 0xffff0000u)),
                                                                      __uint_as_float((uint32_t)v.y << 16), rcp_apx(__uint_as_float((uint32_t)v.y & 0xffff0000u)));
            } else {
                const int ch = j & 7, kg = (j >> 3) & 3;
                const unsigned char* src = stg + A1_SM_R + (j >> 5) * 10240;
                mbar_wait(bar_r, 0);
                uint4 v[20];
#pragma unroll
                for (int k = 0; k < 20; k++) v[k] = *reinterpret_cast<const uint4*>(src + (4 * k + kg) * 128 + ((ch ^ ((4 * k + kg) & 7)) << 4));
                const uint4 pv = *reinterpret_cast<const uint4*>(src + (ch << 4));
                float s[8], q[8], p0[8] = {__uint_as_float(pv.x << 16), __uint_as_float(pv.x & 0xffff0000u), __uint_as_float(pv.y << 16), __uint_as_float(pv.y & 0xffff0000u),
                                           __uint_as_float(pv.z << 16), __uint_as_float(pv.z & 0xffff0000u), __uint_as_float(pv.w << 16), __uint_as_float(pv.w & 0xffff0000u)};
#pragma unroll
                for (int i = 0; i < 8; i++) { s[i] = 0.f; q[i] = 0.f; }
#pragma unroll
                for (int k = 0; k < 20; k++) {
                    const uint32_t w[4] = {v[k].x, v[k].y, v[k].z, v[k].w};
#pragma unroll
                    for (int i = 0; i < 4; i++) {
                        const float a = __uint_as_float(w[i] << 16) - p0[2 * i], b = __uint_as_float(w[i] & 0xffff0000u) - p0[2 * i + 1];
                        s[2 * i] += a; s[2 * i + 1] += b; q[2 * i] = fmaf(a, a, q[2 * i]); q[2 * i + 1] = fmaf(b, b, q[2 * i + 1]);
                    }
                }
#pragma unroll
                for (int i = 0; i < 4; i++) {
                    const bool up = kg & 2;
                    const float ss = __shfl_xor_sync(~0u, up ? s[i] : s[i + 4], 16), qq = __shfl_xor_sync(~0u, up ? q[i] : q[i + 4], 16);
                    s[i] = (up ? s[i + 4] : s[i]) + ss; q[i] = (up ? q[i + 4] : q[i]) + qq; p0[i] = up ? p0[i + 4] : p0[i];
                }
#pragma unroll
                for (int i = 0; i < 2; i++) {
                    const bool up = kg & 1;
                    const float ss = __shfl_xor_sync(~0u, up ? s[i] : s[i + 2], 8), qq = __shfl_xor_sync(~0u, up ? q[i] : q[i + 2], 8);
                    s[i] = (up ? s[i + 2] : s[i]) + ss; q[i] = (up ? q[i + 2] : q[i]) + qq; p0[i] = up ? p0[i + 2] : p0[i];
                }
#pragma unroll
                for (int r = 0; r < 2; r++) {
                    const float d = s[r] * (1.0f / 80.0f);
                    st_tag2(g_part + (mb * 8 + hg) * 128 + 64 * r + j, __float_as_uint(p0[r] + d), __float_as_uint(fmaxf(fmaf(-d, s[r], q[r]), 0.f)), tag);
                }
                const ulonglong2* gp = g_part + mb * 8 * 128 + j;
#pragma unroll 1
                for (int it = 0; it < SPIN_MAX; it++) {
                    if (__all_sync(~0u, tag_ok(ld_tag2(gp + (j & 7) * 128 + 64), tag))) break;
                    __nanosleep(200);
                }
                ulonglong2 pw[16];
#pragma unroll 1
                for (int it = 0; it < SPIN_MAX; it++) {
                    bool ok = true;
#pragma unroll
                    for (int k = 0; k < 16; k++) pw[k] = ld_tag2(gp + k * 64);
#pragma unroll
                    for (int k = 0; k < 16; k++) ok = ok && tag_ok(pw[k], tag);
                    if (ok) break;
                    __nanosleep(200);
                }
                float o[4];
#pragma unroll
                for (int r = 0; r < 2; r++) {
                    float mean = 0.f, m2 = 0.f;
#pragma unroll
                    for (int k = 0; k < 8; k++) mean += __uint_as_float((uint32_t)pw[2 * k + r].x);
                    mean *= 0.125f;
#pragma unroll
                    for (int k = 0; k < 8; k++) {
                        const float dm = __uint_as_float((uint32_t)pw[2 * k + r].x) - mean;
                        m2 += fmaf(80.0f * dm, dm, __uint_as_float((uint32_t)pw[2 * k + r].y));
                    }
                    o[2 * r] = rbf(mean);
                    o[2 * r + 1] = rcp_apx(rbf(sqrt_apx(rbf(rbf(m2 * (1.0f / DM)) + 1e-5f))));
                }
                const int row = (j >> 5) * 64 + (j & 7) * 8 + ((j >> 3) & 3) * 2;
                *reinterpret_cast<float4*>(rst + row) = make_float4(o[0], o[1], o[2], o[3]);
                if (hg == 0) *reinterpret_cast<uint32_t*>(g_piv + SEQ + mb * 128 + row) = __byte_perm(__float_as_uint(o[0]), __float_as_uint(o[2]), 0x7632);
            }
            TSTAMP1T(7, 320);
            __syncwarp();
            if ((tid & 31) == 0) mbar_arrive(bar_stat);
        }
    } else {
        float acc[120];
#pragma unroll
        for (int i = 0; i < 120; i++) acc[i] = 0.f;
        const int lane = tid & 31, warp = w & 7, g = lane >> 2, t = lane & 3;
        if (on) {
            pdl_sync();
            SPAN(1 + 4 * layer, 1);
            TSTAMP1(0);
            if (threadIdx.x == 0) { GSTAMP(g_tim1, 15); }
            TSTAMP3(0);
            if (layer == 0) a1_mainloop<0>(acc, sbase, bars, wg, tile); else a1_mainloop<1>(acc, sbase, bars, wg, tile);
            mbar_wait(bar_stat, 0);
            mbar_wait(bars + 8 * (A1_NST + 3), 1);
            wgmma_wait<0>();
        }
        const float2 sa_ = rst[16 * warp + g], sb_ = rst[16 * warp + g + 8];
        TSTAMP1(2);
        TSTAMP1T(13, 224);
        uint32_t f[30][2];
        auto norm = [&](int j0) {
            float2 cc[10];
#pragma unroll
            for (int j = 0; j < 10; j++) cc[j] = *reinterpret_cast<const float2*>(cs + 8 * (j0 + j) + 2 * t);
#pragma unroll
            for (int j = 0; j < 10; j++) {
                const float* a = acc + 4 * (j0 + j);
                f[j0 + j][0] = pack2(fmaf(-sa_.x, cc[j].x, a[0]) * sa_.y, fmaf(-sa_.x, cc[j].y, a[1]) * sa_.y);
                f[j0 + j][1] = pack2(fmaf(-sb_.x, cc[j].x, a[2]) * sb_.y, fmaf(-sb_.x, cc[j].y, a[3]) * sb_.y);
            }
        };
        norm(10); norm(20);
        if (warp == 7) {
            uint4* hout = g_halo + ((layer * 16 + mb) * 8 + hg) * 320 + lane;
#pragma unroll
            for (int j = 0; j < 20; j += 2)
                asm volatile("st.relaxed.gpu.global.v4.u32 [%0], {%1,%2,%3,%4};" ::"l"(hout + 16 * j), "r"(f[10 + j][0]), "r"(f[10 + j][1]), "r"(f[11 + j][0]), "r"(f[11 + j][1]) : "memory");
        }
        TSTAMP1T(12, 224);
        const uint32_t kvw = sbase + A1_SM_KV + 16 * warp * A1_KVP;
        const uint32_t mrow = kvw + (lane & 15) * A1_KVP + (lane >> 4) * 16;
#pragma unroll
        for (int j = 0; j < 20; j += 2) stsm_x4(mrow + 16 * A1_KVP + 16 * j, f[10 + j][0], f[10 + j][1], f[11 + j][0], f[11 + j][1]);
        __syncwarp();
        if (lane == 0 && on) mbar_arrive(bar_kv + 8 * (warp + 1));
        norm(0);
        TSTAMP1T(10, 64);
        float sc[4][4][4];
        uint32_t qs[4][2];
#pragma unroll
        for (int h = 0; h < 4; h++) {
            const int jb = 5 * (h >> 1) + 3 * (h & 1), js = 5 * (h >> 1) + 2;
            qs[h][0] = (t >> 1) == (h & 1) ? f[js][0] : 0u; qs[h][1] = (t >> 1) == (h & 1) ? f[js][1] : 0u;
#pragma unroll
            for (int nt = 2; nt < 4; nt++) {
#pragma unroll
                for (int e = 0; e < 4; e++) sc[h][nt][e] = 0.f;
                mma_bf16(sc[h][nt], f[jb][0], f[jb][1], f[jb + 1][0], f[jb + 1][1], f[10 + jb][nt - 2], f[11 + jb][nt - 2]);
                mma_bf16_k8(sc[h][nt], qs[h][0], qs[h][1], f[10 + js][nt - 2]);
            }
        }
        if (on) mbar_wait(bar_kv + 8 * warp, 0);
        TSTAMP1(8);
        uint32_t kp[10][2];
#pragma unroll
        for (int j = 0; j < 10; j += 2) ldsm_x4(&kp[j][0], mrow + 16 * j);
#pragma unroll
        for (int h = 0; h < 4; h++) {
            const int jb = 5 * (h >> 1) + 3 * (h & 1), js = 5 * (h >> 1) + 2;
#pragma unroll
            for (int nt = 0; nt < 2; nt++) {
#pragma unroll
                for (int e = 0; e < 4; e++) sc[h][nt][e] = 0.f;
                mma_bf16(sc[h][nt], f[jb][0], f[jb][1], f[jb + 1][0], f[jb + 1][1], kp[jb][nt], kp[jb + 1][nt]);
                mma_bf16_k8(sc[h][nt], qs[h][0], qs[h][1], kp[js][nt]);
            }
        }
        uint32_t vb[10][4];
#pragma unroll
        for (int j = 0; j < 10; j++) ldsm_x4_t(vb[j], kvw + lane * A1_KVP + 160 + 16 * j);
        TSTAMP1T(3, 64);
        const bool odd = g & 1, hi = t > (g >> 1), edge = (mb | warp) == 0;
        float p[4][4], mx[4][2], sum[4][2];
#pragma unroll
        for (int h = 0; h < 4; h++) {
#pragma unroll
            for (int r = 0; r < 2; r++) {
                const float a = odd ? sc[h][1 + r][2 * r + 1] : sc[h][1 + r][2 * r];
                const float b0 = odd ? sc[h][r][2 * r + 1] : sc[h][r][2 * r], b1 = odd ? sc[h][2 + r][2 * r + 1] : sc[h][2 + r][2 * r];
                const uint32_t w1 = pack2(a, hi ? b0 : b1);
                const uint32_t w2 = pack2(__uint_as_float(w1 << 16) * 0.22360679774997896f, __uint_as_float(w1 & 0xffff0000u) * 0.22360679774997896f);
                p[h][2 * r] = __uint_as_float(w2 << 16); p[h][2 * r + 1] = __uint_as_float(w2 & 0xffff0000u);
            }
            if (edge) {
                p[h][0] = -1.0e9f;
                if (hi) { p[h][1] = -1.0e9f; p[h][3] = -1.0e9f; }
            }
            mx[h][0] = fmaxf(p[h][0], p[h][1]); mx[h][1] = fmaxf(p[h][2], p[h][3]);
        }
#pragma unroll
        for (int o = 1; o <= 2; o <<= 1)
#pragma unroll
            for (int h = 0; h < 4; h++)
#pragma unroll
                for (int r = 0; r < 2; r++) mx[h][r] = fmaxf(mx[h][r], __shfl_xor_sync(~0u, mx[h][r], o));
#pragma unroll
        for (int h = 0; h < 4; h++)
#pragma unroll
            for (int r = 0; r < 2; r++) {
                p[h][2 * r] = __expf(p[h][2 * r] - mx[h][r]); p[h][2 * r + 1] = __expf(p[h][2 * r + 1] - mx[h][r]);
                sum[h][r] = p[h][2 * r] + p[h][2 * r + 1];
            }
#pragma unroll
        for (int o = 1; o <= 2; o <<= 1)
#pragma unroll
            for (int h = 0; h < 4; h++)
#pragma unroll
                for (int r = 0; r < 2; r++) sum[h][r] += __shfl_xor_sync(~0u, sum[h][r], o);
        TSTAMP1T(5, 64);
        const uint32_t selA = odd ? 0x1044u : 0x4410u, selB = odd ? 0x3244u : 0x4432u, selH = hi ? selB : 0x4444u, selL = hi ? 0x4444u : selB;
        const uint32_t orow = sbase + A1_SM_O + (16 * warp + (lane & 15)) * 160 + (lane >> 4) * 16;
        uint32_t ob[10][2];
#pragma unroll
        for (int P = 0; P < 2; P++) {
            float os[2][4];
#pragma unroll
            for (int e = 0; e < 2; e++) {
                const int h = 2 * P + e;
                const float i0 = rcp_apx(sum[h][0]), i1 = rcp_apx(sum[h][1]);
                const uint32_t w0 = pack2(p[h][0] * i0, p[h][1] * i0), w1 = pack2(p[h][2] * i1, p[h][3] * i1);
                const uint32_t a00 = __byte_perm(w0, 0, selH), a02 = __byte_perm(w0, 0, selA), a03 = __byte_perm(w1, 0, selH);
                const uint32_t a10 = __byte_perm(w0, 0, selL), a11 = __byte_perm(w1, 0, selA), a13 = __byte_perm(w1, 0, selL);
#pragma unroll
                for (int dt = 0; dt < 3; dt++) {
                    const int j = 5 * P + (dt < 2 ? 3 * e + dt : 2);
                    float o[4] = {0.f, 0.f, 0.f, 0.f};
                    mma_bf16(o, a00, 0u, a02, a03, vb[j][0], vb[j][1]);
                    mma_bf16(o, a10, a11, 0u, a13, vb[j][2], vb[j][3]);
                    if (dt < 2) { ob[j][0] = pack2(o[0], o[1]); ob[j][1] = pack2(o[2], o[3]); }
                    else { os[e][0] = o[0]; os[e][1] = o[1]; os[e][2] = o[2]; os[e][3] = o[3]; }
                }
            }
            ob[5 * P + 2][0] = t < 2 ? pack2(os[0][0], os[0][1]) : pack2(os[1][0], os[1][1]);
            ob[5 * P + 2][1] = t < 2 ? pack2(os[0][2], os[0][3]) : pack2(os[1][2], os[1][3]);
        }
#pragma unroll
        for (int j = 0; j < 10; j += 2) stsm_x4(orow + 16 * j, ob[j][0], ob[j][1], ob[j + 1][0], ob[j + 1][1]);
        fence_async_smem();
        __syncwarp();
        if (on) {
            if (lane == 0) tma_store_2d(&tmOst, hg * 80, mb * 128 + 16 * warp, sbase + A1_SM_O + 16 * warp * 160);
            TSTAMP1T(4, 64);
            TSTAMP1(1);
            GSTAMP(g_tim1, 14);
            SPAN(1 + 4 * layer, 3);
            return;
        }
    }
    mbar_wait(bars + 144, 0);
    mbar_wait(bars + 8 * (A1_NST + 3), 1);
    const uint4* hin = g_halo + ((layer * 16 + mb - 1) * 8 + hg) * 320 + tid - 256;
    uint32_t hv[3][4] = {};
    if (mb > 0) {
#pragma unroll 1
        for (int it = 0; it < SPIN_MAX; it++) {
            bool ok = true;
#pragma unroll
            for (int k = 0; k < 3; k++)
                if (k < 2 || w < 10)
                    asm volatile("ld.relaxed.gpu.global.v4.u32 {%0,%1,%2,%3}, [%4];" : "=r"(hv[k][0]), "=r"(hv[k][1]), "=r"(hv[k][2]), "=r"(hv[k][3]) : "l"(hin + 128 * k) : "memory");
#pragma unroll
            for (int k = 0; k < 3; k++) ok = ok && hv[k][0] != ~0u && hv[k][1] != ~0u && hv[k][2] != ~0u && hv[k][3] != ~0u;
            if (ok) break;
        }
    }
    __syncwarp();
    TSTAMP1T(11, 256);
    const uint32_t hd = sbase + A1_SM_KV + (tid & 15) * A1_KVP + ((tid >> 4) & 1) * 16 + (w - 8) * 32;
#pragma unroll
    for (int k = 0; k < 3; k++)
        if (k < 2 || w < 10) stsm_x4(hd + 128 * k, hv[k][0], hv[k][1], hv[k][2], hv[k][3]);
    __syncwarp();
    if ((tid & 31) == 0) mbar_arrive(bar_kv);
}

constexpr int A2_THREADS = 288;
constexpr int A2_NA = 6;
#define A2_WPRE 4
#define A2_WLEAD 2
#define A2_RPOS 7
constexpr int A2_SM_A = 10 * WO_STAGE;
constexpr int A2_SM_R = A2_SM_A + A2_NA * 16384;
constexpr int A2_SM_BAR = A2_SM_R + 20480;
constexpr int A2_SMEM = A2_SM_BAR + 256 + 1024;

__global__ void __launch_bounds__(A2_THREADS, 1) a2_kernel(const int layer, const __grid_constant__ CUtensorMap tmO, const __grid_constant__ CUtensorMap tmR,
                                                           const __grid_constant__ CUtensorMap tmX1) {
    extern __shared__ unsigned char smraw[];
    const uint32_t sbase = (smem_u32(smraw) + 1023) & ~1023u;
    const uint32_t bars = sbase + A2_SM_BAR, bar_e = bars + 80, bar_r = bars + 128;
    const int tid = threadIdx.x, w = __shfl_sync(~0u, tid >> 5, 0), wg = w >> 2;
    const int tile = sm_tile();
    if (tile >= 128) { sm_idle(2 * layer + 1); return; }
    const int mb = tile >> 3, cg = tile & 7;
    if (wg == 2) {
        const unsigned char* wsrc = reinterpret_cast<const unsigned char*>(g_wo) + cg * 10 * WO_STAGE;
        if (tid == 256) {
            prefetch_tmap(&tmO);
#pragma unroll
            for (int i = 0; i < 17; i++) mbar_init(bars + 8 * i, i >= 10 && i < 16 ? 2 : 1);
            asm volatile("fence.mbarrier_init.release.cluster;" ::: "memory");
#pragma unroll
            for (int kb = 0; kb < A2_WPRE; kb += 2) {
                mbar_expect_tx(bars + 8 * kb, 16384 + 2 * WO_STAGE);
                bulk_load(sbase + kb * WO_STAGE, wsrc + kb * WO_STAGE, 2 * WO_STAGE, bars + 8 * kb);
            }
        }
        __syncwarp();
        asm volatile("bar.arrive 0, 288;" ::: "memory");
        if (tid == 256) {
#pragma unroll
            for (int kb = 0; kb < 10; kb++) if ((kb & 1) || kb >= A2_WPRE) mbar_expect_tx(bars + 8 * kb, (kb & 1) ? 16384 : 16384 + 2 * WO_STAGE);
            mbar_expect_tx(bar_r, 20480);
            pdl_sync();
#pragma unroll 1
            for (int kb = 0; kb < 10; kb++) {
                if (kb >= A2_NA) mbar_wait(bar_e + 8 * (kb - A2_NA), 0);
                tma_load_2d(sbase + A2_SM_A + (kb < A2_NA ? kb : kb - A2_NA) * 16384, &tmO, kb * 64, mb * 128, bars + 8 * kb);
                const int kw = kb + A2_WLEAD;
                if (!(kw & 1) && kw >= A2_WPRE && kw < 10) bulk_load(sbase + kw * WO_STAGE, wsrc + kw * WO_STAGE, 2 * WO_STAGE, bars + 8 * kw);
                if (kb == A2_RPOS) {
                    if (layer == 0) tma_load_2d(sbase + A2_SM_R, &tmR, cg * 80, mb * 128, bar_r);
                    else { tma_load_2d(sbase + A2_SM_R, &tmR, mb * 128, cg * 80, bar_r); tma_load_2d(sbase + A2_SM_R + 10240, &tmR, mb * 128 + 64, cg * 80, bar_r); }
                }
            }
        }
    } else {
        if (tid == 224) { prefetch_tmap(&tmR); prefetch_tmap(&tmX1); sm_started(2 * layer + 1); }
        asm volatile("bar.sync 0, 288;" ::: "memory");
        SPAN(2 + 4 * layer, 0);
        pdl_sync();
        SPAN(2 + 4 * layer, 1);
        TSTAMP2(0);
        TSTAMP4(0);
        if (threadIdx.x == 0) { GSTAMP(g_tim2, 15); }
        const int lane = tid & 31, warp = w, g = lane >> 2, t = lane & 3;
        const int row = layer * SEQ + mb * 128 + 16 * warp + g;
        const unsigned short pv0 = __ldcg(reinterpret_cast<const unsigned short*>(g_piv) + row), pv1 = __ldcg(reinterpret_cast<const unsigned short*>(g_piv) + row + 8);
        float acc[40];
#pragma unroll
        for (int i = 0; i < 40; i++) acc[i] = 0.f;
        const uint64_t da0 = make_desc(sbase + A2_SM_A + wg * 8192, 16, 1024, 1), db0 = make_desc(sbase, 16, 1024, 1);
#pragma unroll 1
        for (int kb = 0; kb < 10; kb++) {
            if (kb == 0) TSTAMP4(11);
            mbar_wait(bars + 8 * kb, 0);
            TSTAMP4(1 + kb);
            wgmma_fence();
#pragma unroll
            for (int kk = 0; kk < 4; kk++) wgmma_n80<0, 0>(acc, da0 + (uint32_t)((kb < A2_NA ? kb : kb - A2_NA) * 1024 + kk * 2), db0 + (uint32_t)(kb * (WO_STAGE / 16) + kk * 2));
            wgmma_commit();
            wgmma_wait<1>();
            if (kb > 0 && kb <= A2_NA && (tid & 127) == 0) mbar_arrive(bar_e + 8 * (kb - 1));
        }
        const uint32_t trow = ((lane & 7) + 8 * (lane >> 4)) * 128 + (((2 * (warp & 3) + ((lane >> 3) & 1)) ^ (lane & 7)) << 4);
        uint32_t xr[10][2];
        mbar_wait(bar_r, 0);
        if (layer == 0) {
#pragma unroll
            for (int j = 0; j < 10; j += 2) ldsm_x4(&xr[j][0], sbase + A2_SM_R + (16 * warp + (lane & 15)) * 160 + (lane >> 4) * 16 + 16 * j);
        } else {
#pragma unroll
            for (int j = 0; j < 10; j += 2) ldsm_x4_t(&xr[j][0], sbase + A2_SM_R + wg * 10240 + trow + 1024 * j);
        }
        mbar_wait(bar_e + 8 * (4 + wg), 0);
        wgmma_wait<0>();
        TSTAMP2(1);
        const float p0 = __uint_as_float((uint32_t)pv0 << 16), p1 = __uint_as_float((uint32_t)pv1 << 16);
        float s[4] = {0.f, 0.f, 0.f, 0.f};
#pragma unroll
        for (int j = 0; j < 10; j++) {
#pragma unroll
            for (int hh = 0; hh < 2; hh++) {
                const uint32_t a = pack2(acc[4 * j + 2 * hh], acc[4 * j + 2 * hh + 1]);
                const __nv_bfloat162 r = __hadd2_rn(*reinterpret_cast<const __nv_bfloat162*>(&xr[j][hh]), *reinterpret_cast<const __nv_bfloat162*>(&a));
                const uint32_t w = *reinterpret_cast<const uint32_t*>(&r);
                xr[j][hh] = w;
                const float d0 = __uint_as_float(w << 16) - (hh ? p1 : p0), d1 = __uint_as_float(w & 0xffff0000u) - (hh ? p1 : p0);
                s[2 * hh] += d0 + d1;
                s[2 * hh + 1] = fmaf(d0, d0, fmaf(d1, d1, s[2 * hh + 1]));
            }
        }
        const uint32_t so = sbase + A2_SM_A + (4 + wg) * 16384;
#pragma unroll
        for (int j = 0; j < 10; j += 2) stsm_x4_t(so + trow + 1024 * j, xr[j][0], xr[j][1], xr[j + 1][0], xr[j + 1][1]);
        fence_async_smem();
        TSTAMP2(2);
#pragma unroll
        for (int o = 1; o <= 2; o <<= 1)
#pragma unroll
            for (int i = 0; i < 4; i++) s[i] += __shfl_xor_sync(~0u, s[i], o);
        if (t < 2) asm volatile("red.relaxed.gpu.global.add.v2.f32 [%0], {%1, %2};" ::"l"(g_sum + layer * SEQ + (g >> 1) * 512 + (mb * 16 + 2 * warp + t) * 2 + (g & 1)), "f"(t ? s[2] : s[0]), "f"(t ? s[3] : s[1]) : "memory");
        if (wg) asm volatile("bar.sync 2, 128;" ::: "memory"); else asm volatile("bar.sync 1, 128;" ::: "memory");
        TSTAMP2(3);
        if ((tid & 127) == 0) tma_store_2d(&tmX1, mb * 128 + 64 * wg, cg * 80, so);
        TSTAMP2(4);
        GSTAMP(g_tim2, 14);
        SPAN(2 + 4 * layer, 3);
    }
}

static int h_nsm;
static CUtensorMap h_tmX0, h_tmX1, h_tmOst, h_tmO, h_tmR0, h_tmR1, h_tmX1st, h_tmOut;
typedef CUresult (*PFN_encodeTiled)(CUtensorMap*, CUtensorMapDataType, cuuint32_t, void*, const cuuint64_t*, const cuuint64_t*,
                                    const cuuint32_t*, const cuuint32_t*, CUtensorMapInterleave, CUtensorMapSwizzle,
                                    CUtensorMapL2promotion, CUtensorMapFloatOOBfill);
static void make_tmap(CUtensorMap* tm, const void* ptr, uint64_t cols, uint64_t rows, uint32_t bc, uint32_t br, CUtensorMapSwizzle sw, uint64_t pitch = 0) {
    static PFN_encodeTiled fn = nullptr;
    if (!fn) {
        void* p = nullptr; cudaDriverEntryPointQueryResult qr;
        cudaGetDriverEntryPoint("cuTensorMapEncodeTiled", &p, cudaEnableDefault, &qr);
        fn = (PFN_encodeTiled)p;
    }
    cuuint64_t dims[2] = {cols, rows}; cuuint64_t strides[1] = {(pitch ? pitch : cols) * 2};
    cuuint32_t box[2] = {bc, br}; cuuint32_t es[2] = {1, 1};
    fn(tm, CU_TENSOR_MAP_DATA_TYPE_BFLOAT16, 2, const_cast<void*>(ptr), dims, strides, box, es, CU_TENSOR_MAP_INTERLEAVE_NONE, sw,
       CU_TENSOR_MAP_L2_PROMOTION_L2_128B, CU_TENSOR_MAP_FLOAT_OOB_FILL_NONE);
}
template <typename... Args>
static void launch_pdl(void (*kern)(Args...), int grid, int block, int smem, Args... args) {
    cudaLaunchConfig_t cfg = {};
    cfg.gridDim = dim3(grid); cfg.blockDim = dim3(block); cfg.dynamicSmemBytes = smem; cfg.stream = cudaStreamPerThread;
    cudaLaunchAttribute at[1];
    at[0].id = cudaLaunchAttributeProgrammaticStreamSerialization; at[0].val.programmaticStreamSerializationAllowed = 1;
    cfg.attrs = at; cfg.numAttrs = 1;
    cudaLaunchKernelEx(&cfg, kern, args...);
}
static void launch_stage(int k, void* const* d_in, void* d_out) {
    const KgIn kg = {(const bf16*)d_in[4], (const bf16*)d_in[5], (const bf16*)d_in[6], (const bf16*)d_in[7], (const bf16*)d_in[8], (const bf16*)d_in[0], (const bf16*)d_in[1], (const bf16*)d_in[2]};
    switch (k) {
        case 0: kgen_kernel<<<DM, KG_THREADS, 0, cudaStreamPerThread>>>(kg); break;
        case 1: launch_pdl(a1_kernel, h_nsm, A1_THREADS, A1_SMEM, 0, (const bf16*)d_in[0], h_tmX0, h_tmR1, h_tmOst); break;
        case 2: launch_pdl(a2_kernel, h_nsm, A2_THREADS, A2_SMEM, 0, h_tmO, h_tmR0, h_tmX1st); break;
        case 3: launch_pdl(conv_kernel, DM / CV_CPB, CV_THREADS, CV_SMEM, (const bf16*)d_in[9], 0, h_tmOut); break;
        case 5: launch_pdl(a1_kernel, h_nsm, A1_THREADS, A1_SMEM, 1, (const bf16*)d_in[0], h_tmX1, h_tmR1, h_tmOst); break;
        case 6: launch_pdl(a2_kernel, h_nsm, A2_THREADS, A2_SMEM, 1, h_tmO, h_tmR1, h_tmX1st); break;
        case 7: launch_pdl(conv_kernel, DM / CV_CPB, CV_THREADS, CV_SMEM, (const bf16*)d_in[9], 1, h_tmOut); break;
        default: break;
    }
}
static int n_stage_kernels() { return 9; }
static const char* stage_name(int k) { const char* n[] = {"kgen", "a1", "a2", "conv", "tr", "a1", "a2", "conv", "tr"}; return n[k]; }

extern "C" void kernel_launch(void* const* d_in, const int* in_sizes, int n_in, void* d_out, int out_size) {
    (void)in_sizes; (void)n_in; (void)out_size;
    static const void *p_in = nullptr, *p_out = nullptr;
    if (p_in != d_in[0] || p_out != d_out) {
        cudaFuncSetAttribute(conv_kernel, cudaFuncAttributeMaxDynamicSharedMemorySize, CV_SMEM);
        cudaFuncSetAttribute(kgen_kernel, cudaFuncAttributePreferredSharedMemoryCarveout, 100);
        cudaFuncSetAttribute(a1_kernel, cudaFuncAttributeMaxDynamicSharedMemorySize, A1_SMEM);
        cudaFuncSetAttribute(a2_kernel, cudaFuncAttributeMaxDynamicSharedMemorySize, A2_SMEM);
        int dev; cudaGetDevice(&dev); cudaDeviceGetAttribute(&h_nsm, cudaDevAttrMultiProcessorCount, dev);
        if (h_nsm != 132) h_nsm = 128;
        void *po, *px1, *px2;
        cudaGetSymbolAddress(&po, g_o); cudaGetSymbolAddress(&px1, g_x1T); cudaGetSymbolAddress(&px2, g_xcT);
        make_tmap(&h_tmO, po, 640, 2048, 64, 128, CU_TENSOR_MAP_SWIZZLE_128B);
        make_tmap(&h_tmOst, po, 640, 2048, 80, 16, CU_TENSOR_MAP_SWIZZLE_NONE);
        make_tmap(&h_tmX0, d_in[0], 640, 2048, 64, 128, CU_TENSOR_MAP_SWIZZLE_128B);
        make_tmap(&h_tmX1, px2, 2048, 640, 64, 64, CU_TENSOR_MAP_SWIZZLE_128B, XCP);
        make_tmap(&h_tmR0, d_in[0], 640, 2048, 80, 128, CU_TENSOR_MAP_SWIZZLE_NONE);
        make_tmap(&h_tmR1, px2, 2048, 640, 64, 80, CU_TENSOR_MAP_SWIZZLE_128B, XCP);
        make_tmap(&h_tmX1st, px1, 2048, 640, 64, 80, CU_TENSOR_MAP_SWIZZLE_128B, XCP);
        make_tmap(&h_tmOut, d_out, 640, 2048, 80, 8, CU_TENSOR_MAP_SWIZZLE_NONE);
        p_in = d_in[0]; p_out = d_out;
    }
    for (int k = 0; k < n_stage_kernels(); k++) launch_stage(k, d_in, d_out);
}
```

```cpp
#include <cuda_runtime.h>
#include <cuda_bf16.h>
#include <stdint.h>
#include <cuda.h>

typedef __nv_bfloat16 bf16;

constexpr int SEQ = 2048;
constexpr int DM = 640;
constexpr int NMODE = 192;

__device__ __forceinline__ float bf2f(bf16 v) { return __bfloat162float(v); }
__device__ __forceinline__ float rbf(float v) {
    uint32_t r;
    asm("cvt.rn.bf16x2.f32 %0, %1, %2;" : "=r"(r) : "f"(v), "f"(0.f));
    return __uint_as_float(r);
}
__device__ __forceinline__ uint32_t pack2(float lo, float hi) {
    __nv_bfloat162 t = __floats2bfloat162_rn(lo, hi);
    return *reinterpret_cast<uint32_t*>(&t);
}
__device__ __forceinline__ void pdl_sync() {
    asm volatile("griddepcontrol.wait;" ::: "memory");
    asm volatile("griddepcontrol.launch_dependents;" ::: "memory");
}
__device__ __forceinline__ float sqrt_apx(float v) { float r; asm("sqrt.approx.ftz.f32 %0, %1;" : "=f"(r) : "f"(v)); return r; }
__device__ __forceinline__ float rcp_apx(float v) { float r; asm("rcp.approx.ftz.f32 %0, %1;" : "=f"(r) : "f"(v)); return r; }
__device__ __forceinline__ uint32_t smem_u32(const void* p) { return (uint32_t)__cvta_generic_to_shared(p); }

constexpr int TPAD = 16;
constexpr int DLEN = 544;
constexpr int TAP_W2 = DLEN * 8, TAP_W3 = TAP_W2 + 768, TAP_C = TAP_W3 + 768, TAPB = TAP_C + 384;
__device__ __align__(128) uint4 g_tap[DM * 128];
#define XPAD 64
constexpr int XCP = SEQ + XPAD;
__device__ __align__(128) bf16 g_x1T[DM * XCP];
__device__ __align__(128) bf16 g_xcT[DM * XCP];
__device__ __align__(128) bf16 g_o[SEQ * DM];
constexpr int WQ_STAGE = 240 * 128, WO_STAGE = 80 * 128;
__device__ __align__(128) uint4 g_wq[8 * 10 * WQ_STAGE / 16];
__device__ __align__(128) uint4 g_wo[8 * 10 * WO_STAGE / 16];
__device__ __align__(16) float g_csp[10 * 1920];
__device__ __align__(16) float2 g_sum[2 * SEQ];
__device__ __align__(16) bf16 g_piv[2 * SEQ];
__device__ __align__(128) bf16 g_yT[DM * XCP];
__device__ uint32_t g_epoch;
__device__ __align__(16) unsigned long long g_rstat[SEQ];
__device__ ulonglong2 g_part[16 * 8 * 128];
__device__ uint4 g_halo[2 * 128 * 320];
__device__ __forceinline__ unsigned long long tagw(uint32_t payload, uint32_t tag) { return ((unsigned long long)tag << 32) | payload; }
__device__ __forceinline__ void st_tag2(ulonglong2* p, uint32_t a, uint32_t b, uint32_t tag) {
    asm volatile("st.global.cg.v2.u64 [%0], {%1, %2};" ::"l"(p), "l"(tagw(a, tag)), "l"(tagw(b, tag)) : "memory");
}
__device__ __forceinline__ ulonglong2 ld_tag2(const ulonglong2* p) {
    ulonglong2 v;
    asm volatile("ld.relaxed.gpu.global.v2.u64 {%0, %1}, [%2];" : "=l"(v.x), "=l"(v.y) : "l"(p) : "memory");
    return v;
}
__device__ __forceinline__ bool tag_ok(ulonglong2 v, uint32_t tag) { return (uint32_t)(v.x >> 32) == tag && (uint32_t)(v.y >> 32) == tag; }
__device__ __forceinline__ uint32_t ld_epoch() { uint32_t v; asm volatile("ld.relaxed.gpu.global.u32 %0, [%1];" : "=r"(v) : "l"(&g_epoch) : "memory"); return v + 1; }
constexpr int SPIN_MAX = 1 << 20;
__device__ uint32_t g_started[4];
__device__ __forceinline__ void sm_started(int slot) { asm volatile("red.relaxed.gpu.global.add.u32 [%0], 1;" ::"l"(g_started + slot) : "memory"); }
__device__ __noinline__ void sm_idle(int slot) {
    if (threadIdx.x) return;
    sm_started(slot);
    const uint32_t want = ld_epoch() * gridDim.x;
    pdl_sync();
#pragma unroll 1
    for (int it = 0; it < SPIN_MAX; it++) {
        uint32_t v;
        asm volatile("ld.relaxed.gpu.global.u32 %0, [%1];" : "=r"(v) : "l"(g_started + slot) : "memory");
        if ((int)(v - want) >= 0) break;
        __nanosleep(100);
    }
}
__device__ __forceinline__ int sm_tile() {
    uint32_t s;
    asm volatile("mov.u32 %0, %smid;" : "=r"(s));
    const uint32_t h = (s - 64) >> 1, q = (h * 37) >> 8;
    const int t0 = ((s >> 1) & 7) * 16 + (s >> 4) * 2 + (s & 1), t1 = (1 + h - 7 * q) * 16 + 8 + q * 2 + (s & 1), t2 = s - 124 < 8 ? s - 116 : 128;
    return gridDim.x == 128 ? (int)blockIdx.x : s < 64 ? t0 : s < 120 ? t1 : t2;
}
#define DBG_SYMS
#define TSTAMP(i)
#define TSTAMP1(i)
#define TSTAMP1T(i, t)
#define TSTAMP1X(i, t)
#define SPAN(k, i)
#define GSTAMP(arr, i)
#define TSTAMP2(i)
#define TSTAMP3(i)
#define TSTAMP4(i)
#define TSTAMPK(i, t)

__device__ __forceinline__ float2 cexp_at(float wr2, float wi, float p) {
    float er;
    asm("ex2.approx.ftz.f32 %0, %1;" : "=f"(er) : "f"(wr2 * p));
    float th = wi * p;
    const float k = rintf(th * 0.15915494309189535f);
    th = fmaf(k, -6.2831854820251465f, th);
    th = fmaf(k, 1.7484555314695172e-7f, th);
    return make_float2(er * __cosf(th), er * __sinf(th));
}
__device__ __forceinline__ float2 cmul(float2 a, float2 b) {
    return make_float2(fmaf(a.x, b.x, -a.y * b.y), fmaf(a.x, b.y, a.y * b.x));
}
__device__ __forceinline__ float2 csqr(float2 a) { return make_float2(fmaf(a.x, a.x, -a.y * a.y), (a.x + a.x) * a.y); }
__device__ __forceinline__ uint32_t packh(float2 v) {
    uint32_t r;
    asm("cvt.rn.f16x2.f32 %0, %1, %2;" : "=r"(r) : "f"(v.y), "f"(v.x));
    return r;
}
__device__ __forceinline__ void mma_f16(float* d, uint32_t a0, uint32_t a1, uint32_t a2, uint32_t a3, uint32_t b0, uint32_t b1) {
    asm volatile("mma.sync.aligned.m16n8k16.row.col.f32.f16.f16.f32 {%0,%1,%2,%3}, {%4,%5,%6,%7}, {%8,%9}, {%0,%1,%2,%3};"
                 : "+f"(d[0]), "+f"(d[1]), "+f"(d[2]), "+f"(d[3]) : "r"(a0), "r"(a1), "r"(a2), "r"(a3), "r"(b0), "r"(b1));
}

struct KgIn { const bf16 *logA, *Aim, *Cre, *Cim, *logdt, *x, *wqkv, *wo; uint4 *tap, *wq, *wop, *halo, *sum; float* csp; };
constexpr int KG_THREADS = NMODE / 2;

__global__ void __launch_bounds__(KG_THREADS, 5) kgen_kernel(const KgIn in) {
    __shared__ __align__(128) uint4 tab[3 * 896];
    const int d = blockIdx.x, tid = threadIdx.x, lane = tid & 31, warp = tid >> 5;
    SPAN(0, 0); SPAN(0, 1);
    TSTAMPK(0, 0);
    asm volatile("griddepcontrol.launch_dependents;" ::: "memory");
    const bf16 pdt = in.logdt[d];
    const uint32_t pla = reinterpret_cast<const uint32_t*>(in.logA)[d * KG_THREADS + tid], pai = reinterpret_cast<const uint32_t*>(in.Aim)[d * KG_THREADS + tid];
    const uint32_t pcr = reinterpret_cast<const uint32_t*>(in.Cre)[d * KG_THREADS + tid], pci = reinterpret_cast<const uint32_t*>(in.Cim)[d * KG_THREADS + tid];
    const bf16* pfq = tid < 30 ? in.wqkv + (size_t)(d * 30 + tid) * 64 : tid < 40 ? in.wo + (size_t)(d * 10 + tid - 30) * 64 : in.x + (size_t)(d * 32 + tid - 40) * 64;
    if (tid < 72) asm volatile("prefetch.global.L2 [%0];" ::"l"(pfq));
    asm volatile("st.global.v4.u32 [%0], {%1,%1,%1,%1};" ::"l"(in.halo + d * 128 + tid), "r"(~0u));
    if (tid < 32) asm volatile("st.global.v4.u32 [%0], {%1,%1,%1,%1};" ::"l"(in.halo + d * 128 + 96 + tid), "r"(~0u));
    const uint32_t tw = smem_u32(tab) + warp * 14336;
    const int g = lane >> 2, t = lane & 3;
    const uint32_t sta = tw + lane * 128 + ((2 * (lane & 3) + ((lane >> 2) & 1)) << 4);
    const uint32_t lda = tw + t * 128 + ((g ^ (2 * t)) << 4);
    const uint32_t stb = tw + 12288 + lane * 64 + ((4 * ((lane >> 1) & 1) + ((lane >> 2) & 3)) << 3);
    const uint32_t ldb = tw + 12288 + t * 64 + ((g ^ (4 * (t >> 1))) << 3);
    auto sts4 = [&](int e, int off, uint32_t a, uint32_t b, uint32_t c, uint32_t dd) {
        asm volatile("st.shared.v4.u32 [%0], {%1,%2,%3,%4};" ::"r"((sta ^ (e << 4)) + off), "r"(a), "r"(b), "r"(c), "r"(dd) : "memory");
    };
    auto lds4 = [&](int sp, int off, uint32_t* r) {
        asm volatile("ld.shared.v4.u32 {%0,%1,%2,%3}, [%4];" : "=r"(r[0]), "=r"(r[1]), "=r"(r[2]), "=r"(r[3]) : "r"((lda ^ ((sp & 1) << 4)) + sp * 512 + off) : "memory");
    };
    const float dt = rbf(expf(bf2f(pdt)));
    float2 C[2], y1[2], z8[2], y128[2];
    float cmax = 0.f;
#pragma unroll
    for (int m = 0; m < 2; m++) {
        const float wr2 = -rbf(expf(__uint_as_float(m ? pla & 0xffff0000u : pla << 16))) * dt * 1.4426950408889634f;
        const float wi = __uint_as_float(m ? pai & 0xffff0000u : pai << 16) * dt;
        C[m] = make_float2(__uint_as_float(m ? pcr & 0xffff0000u : pcr << 16) * dt, -__uint_as_float(m ? pci & 0xffff0000u : pci << 16) * dt);
        cmax = fmaxf(cmax, fmaxf(fabsf(C[m].x), fabsf(C[m].y)));
        y1[m] = cexp_at(wr2, -wi, 1.f); z8[m] = cexp_at(wr2, wi, 8.f); y128[m] = cexp_at(wr2, -wi, 128.f);
    }
    const int ex = min(max((int)(__reduce_max_sync(~0u, __float_as_uint(cmax)) >> 23), 20), 240);
    const float scale = __uint_as_float((uint32_t)(127 + 10 + 127 - ex) << 23), unscale = 2.0f * __uint_as_float((uint32_t)(ex - 10) << 23);
    TSTAMPK(4, 0);
    float k2048 = 0.f;
    float acc[5][4];
#pragma unroll
    for (int j = 0; j < 5; j++)
#pragma unroll
        for (int k = 0; k < 4; k++) acc[j][k] = 0.f;
    uint32_t af[8][4];
    {
        float2 h0[2], h1[2], g0[2], g1[2], g2[2], g2b[2], g3[2], g4[2], y2[2], y4[2];
#pragma unroll
        for (int m = 0; m < 2; m++) {
            h0[m] = make_float2(1.f, 0.f); h1[m] = csqr(csqr(csqr(z8[m])));
            g0[m] = make_float2(C[m].x * scale, C[m].y * scale);
            g1[m] = cmul(g0[m], y128[m]);
            const float2 y256 = csqr(y128[m]), y512 = csqr(y256);
            g2b[m] = g2[m] = cmul(g0[m], y256); g3[m] = cmul(g0[m], y512); g4[m] = cmul(g3[m], y512);
            y2[m] = csqr(y1[m]); y4[m] = csqr(y2[m]);
            const float2 y1024 = csqr(y512);
            k2048 += fmaf(g4[m].x, y1024.x, -g4[m].y * y1024.y);
        }
#pragma unroll
        for (int e = 0; e < 8; e++) {
            sts4(e, 0, packh(h0[0]), packh(h1[0]), packh(h0[1]), packh(h1[1]));
            sts4(e, 4096, packh(g0[0]), packh(g0[1]), packh(g1[0]), packh(g1[1]));
#pragma unroll
            for (int m = 0; m < 2; m++)
                if (e < 7) { h0[m] = e ? cmul(h0[m], z8[m]) : z8[m]; h1[m] = cmul(h1[m], z8[m]); g0[m] = cmul(g0[m], y1[m]); g1[m] = cmul(g1[m], y1[m]); }
            if (e < 5) k2048 += __shfl_xor_sync(~0u, k2048, 1 << e);
        }
        __syncwarp();
#pragma unroll
        for (int e = 0; e < 8; e++) {
            uint32_t b[4];
            lds4(e, 0, af[e]); lds4(e, 4096, b);
            sts4(e, 8192, packh(g2[0]), packh(g2[1]), packh((e & 1) ? cmul(g3[0], y4[0]) : g3[0]), packh((e & 1) ? cmul(g3[1], y4[1]) : g3[1]));
            asm volatile("st.shared.v2.u32 [%0], {%1,%2};" ::"r"(stb ^ (e << 3)), "r"(packh(g4[0])), "r"(packh(g4[1])) : "memory");
#pragma unroll
            for (int m = 0; m < 2; m++)
                if (e < 7) {
                    g2[m] = e == 3 ? cmul(g2b[m], y128[m]) : cmul(g2[m], y2[m]);
                    if (e & 1) g3[m] = cmul(g3[m], y128[m]);
                    g4[m] = cmul(g4[m], y128[m]);
                }
            mma_f16(acc[0], af[e][0], af[e][1], af[e][2], af[e][3], b[0], b[1]);
            mma_f16(acc[1], af[e][0], af[e][1], af[e][2], af[e][3], b[2], b[3]);
        }
    }
    TSTAMPK(6, 0);
    const int job = warp * DM + d;
    const bool isq = job < 1200;
    uint32_t sw[16];
    unsigned char* sdst = nullptr;
    int sn = 0;
    if (job < 1600) {
        const int j2 = isq ? job : job - 1200, kb = j2 % 10, col = (j2 / 10) * 16 + (lane >> 3) * 4;
        if (isq) {
            const int sec = col / DM, r = col - sec * DM, hg = r / 80;
            sn = hg * 160 + sec * 80 + r;
            sdst = reinterpret_cast<unsigned char*>(in.wq) + (hg * 9 + kb) * WQ_STAGE;
        } else {
            sn = col;
            sdst = reinterpret_cast<unsigned char*>(in.wop) + ((col / 80) * 9 + kb) * WO_STAGE;
        }
        const int pitch = isq ? 3 * DM : DM;
        const bf16* src = (isq ? in.wqkv : in.wo) + (size_t)(kb * 64 + (lane & 7) * 8) * pitch + col;
#pragma unroll
        for (int i = 0; i < 8; i++) {
            const uint2 v = __ldg(reinterpret_cast<const uint2*>(src + i * pitch));
            sw[2 * i] = v.x; sw[2 * i + 1] = v.y;
        }
        sn += kb << 16;
    } else if (job < 1600 + 64) {
        in.sum[(job - 1600) * 32 + lane] = make_uint4(0, 0, 0, 0);
    }
    __syncwarp();
#pragma unroll
    for (int sp = 0; sp < 8; sp++) {
        uint32_t c[4], e0, e1;
        lds4(sp, 8192, c);
        asm volatile("ld.shared.v2.u32 {%0,%1}, [%2];" : "=r"(e0), "=r"(e1) : "r"((ldb ^ ((sp & 3) << 3)) + sp * 256) : "memory");
        mma_f16(acc[2], af[sp][0], af[sp][1], af[sp][2], af[sp][3], c[0], c[1]);
        mma_f16(acc[3], af[sp][0], af[sp][1], af[sp][2], af[sp][3], c[2], c[3]);
        mma_f16(acc[4], af[sp][0], af[sp][1], af[sp][2], af[sp][3], e0, e1);
    }
    {
        float* Pp = reinterpret_cast<float*>(tab + warp * 896);
#pragma unroll
        for (int h = 0; h < 2; h++) {
            const int b = g + 8 * h;
            *reinterpret_cast<float2*>(Pp + 8 * b + 2 * t) = make_float2(acc[0][2 * h] * unscale, acc[0][2 * h + 1] * unscale);
            *reinterpret_cast<float2*>(Pp + 128 + 8 * b + 2 * t) = make_float2(acc[1][2 * h] * unscale, acc[1][2 * h + 1] * unscale);
            *reinterpret_cast<float2*>(Pp + 256 + 4 * b + 2 * (t & 1) + 64 * (t >> 1)) = make_float2(acc[2][2 * h] * unscale, acc[2][2 * h + 1] * unscale);
            *reinterpret_cast<float2*>(Pp + 384 + 2 * b + 32 * t) = make_float2(acc[3][2 * h] * unscale, acc[3][2 * h + 1] * unscale);
            Pp[512 + b + 32 * t] = acc[4][2 * h] * unscale;
            Pp[512 + b + 32 * t + 16] = acc[4][2 * h + 1] * unscale;
        }
        if (lane == 0) Pp[640] = k2048 * unscale;
    }
    TSTAMPK(7, 0);
    __syncthreads();
    TSTAMPK(9, 0);
    const float* Kp = reinterpret_cast<const float*>(tab);
    auto ksum = [&](int i) -> float { return (Kp[i] + Kp[3584 + i]) + Kp[7168 + i]; };
    auto ksum4 = [&](int q) -> float4 {
        const float4 a = reinterpret_cast<const float4*>(Kp)[q], b = reinterpret_cast<const float4*>(Kp)[896 + q], c = reinterpret_cast<const float4*>(Kp)[1792 + q];
        return make_float4((a.x + b.x) + c.x, (a.y + b.y) + c.y, (a.z + b.z) + c.z, (a.w + b.w) + c.w);
    };
    {
        uint2* E4 = reinterpret_cast<uint2*>(in.tap + d * 128);
        float4 v = ksum4(tid), u = ksum4(96 + min(tid, 64));
        const float cor = rbf(ksum(tid == 95 ? 384 : 512));
        if (tid == 95) v.w -= cor;
        if (tid == 31) u.w -= cor;
        const uint32_t lo = pack2(v.x, v.y), hi = pack2(v.z, v.w);
        if (tid < 64) {
            E4[6 + tid] = make_uint2(lo, hi);
            E4[(tid < 32 ? 159 : 209 - 32) + tid] = make_uint2(pack2(u.x, u.y), pack2(u.z, u.w));
        } else {
            const uint32_t nx = __shfl_down_sync(~0u, lo, 1);
            in.tap[d * 128 + 35 + tid - 64] = make_uint4(__byte_perm(lo, 0, 0x1010), __byte_perm(lo, hi, 0x5432), __byte_perm(hi, 0, 0x1010), __byte_perm(hi, tid == 95 ? 0u : nx, 0x5432));
            if (tid == 64) E4[241] = make_uint2(pack2(u.x, 0.f), 0u);
        }
    }
    if (job < 1600) {
        const int c = lane & 7, n = sn & 0xffff;
#pragma unroll
        for (int q = 0; q < 4; q++) {
            uint32_t w[4];
#pragma unroll
            for (int j = 0; j < 4; j++) w[j] = __byte_perm(sw[4 * j + (q >> 1)], sw[4 * j + 2 + (q >> 1)], (q & 1) ? 0x7632 : 0x5410);
            *reinterpret_cast<uint4*>(sdst + (n + q) * 128 + ((c ^ ((n + q) & 7)) << 4)) = make_uint4(w[0], w[1], w[2], w[3]);
        }
    }
    TSTAMPK(10, 0);
    if (isq) {
        float4 a = make_float4(0.f, 0.f, 0.f, 0.f);
#pragma unroll
        for (int i = 0; i < 8; i++) {
            a.x += __uint_as_float(sw[2 * i] << 16); a.y += __uint_as_float(sw[2 * i] & 0xffff0000u);
            a.z += __uint_as_float(sw[2 * i + 1] << 16); a.w += __uint_as_float(sw[2 * i + 1] & 0xffff0000u);
        }
#pragma unroll
        for (int o = 1; o <= 4; o <<= 1) {
            a.x += __shfl_xor_sync(~0u, a.x, o); a.y += __shfl_xor_sync(~0u, a.y, o);
            a.z += __shfl_xor_sync(~0u, a.z, o); a.w += __shfl_xor_sync(~0u, a.w, o);
        }
        if ((lane & 7) == 0) *reinterpret_cast<float4*>(in.csp + (sn >> 16) * 1920 + (sn & 0xffff)) = a;
    }
    TSTAMPK(11, 0);
    SPAN(0, 3);
}

#define CV_MODE 0
#define CV_SLEEP 100
constexpr int CV_CPB = 5;
constexpr int CV_THREADS = 512;
constexpr int UPADF = 128;
constexpr int ULEN = UPADF + SEQ + 80;
constexpr int XLEN = SEQ + 16;
constexpr int BX_5 = 0, BX_3 = 3264, BX_9 = 6528, BX_7 = 8960, BX_LEN = 11392;
constexpr int CV_SM_T = 0;
constexpr int CV_SM_B = CV_CPB * TAPB;
constexpr int CV_SM_U = CV_SM_B + CV_CPB * BX_LEN;
constexpr int CV_SM_X = CV_SM_U + CV_CPB * ULEN * 2;
constexpr int CV_SM_Y = CV_SM_X + CV_CPB * XLEN * 2;
constexpr int CV_SM_P = CV_SM_Y + CV_CPB * XLEN * 2;
constexpr int CV_SM_CNT = CV_SM_P + 6 * 4096;
constexpr int CV_SM_O = (CV_SM_CNT + 128 + 127) & ~127;
constexpr int CV_SMEM = CV_SM_O + 20480;
static_assert(CV_SM_B % 128 == 0 && CV_SM_CNT % 16 == 0, "layout");

__device__ __forceinline__ void mma_bf16(float* d, uint32_t a0, uint32_t a1, uint32_t a2, uint32_t a3, uint32_t b0, uint32_t b1) {
    asm volatile("mma.sync.aligned.m16n8k16.row.col.f32.bf16.bf16.f32 {%0,%1,%2,%3}, {%4,%5,%6,%7}, {%8,%9}, {%0,%1,%2,%3};"
                 : "+f"(d[0]), "+f"(d[1]), "+f"(d[2]), "+f"(d[3]) : "r"(a0), "r"(a1), "r"(a2), "r"(a3), "r"(b0), "r"(b1));
}
__device__ __forceinline__ void mma_bf16_k8(float* d, uint32_t a0, uint32_t a1, uint32_t b0) {
    asm volatile("mma.sync.aligned.m16n8k8.row.col.f32.bf16.bf16.f32 {%0,%1,%2,%3}, {%4,%5}, {%6}, {%0,%1,%2,%3};"
                 : "+f"(d[0]), "+f"(d[1]), "+f"(d[2]), "+f"(d[3]) : "r"(a0), "r"(a1), "r"(b0));
}
__device__ __forceinline__ void ldsm_x4(uint32_t* r, uint32_t addr) {
    asm volatile("ldmatrix.sync.aligned.m8n8.x4.shared.b16 {%0,%1,%2,%3}, [%4];"
                 : "=r"(r[0]), "=r"(r[1]), "=r"(r[2]), "=r"(r[3]) : "r"(addr));
}

__device__ __forceinline__ void ldsm_x4_t(uint32_t* r, uint32_t addr) {
    asm volatile("ldmatrix.sync.aligned.m8n8.x4.trans.shared.b16 {%0,%1,%2,%3}, [%4];"
                 : "=r"(r[0]), "=r"(r[1]), "=r"(r[2]), "=r"(r[3]) : "r"(addr));
}
__device__ __forceinline__ uint32_t ln2(uint32_t x, uint32_t m, float ra, float rb) {
    const __nv_bfloat162 d = __hsub2(*reinterpret_cast<const __nv_bfloat162*>(&x), *reinterpret_cast<const __nv_bfloat162*>(&m));
    const uint32_t w = *reinterpret_cast<const uint32_t*>(&d);
    return pack2(__uint_as_float(w << 16) * ra, __uint_as_float(w & 0xffff0000u) * rb);
}
__device__ __forceinline__ void cp_async16(uint32_t dst, const void* src) {
    asm volatile("cp.async.cg.shared.global [%0], [%1], 16;" ::"r"(dst), "l"(src));
}
__device__ __forceinline__ void cp_async_wait_all() { asm volatile("cp.async.wait_all;" ::: "memory"); }

template <bool FULL>
__device__ __forceinline__ void direct_pass(float (&acc)[8][4], uint32_t ub, uint32_t o0, uint32_t o1, const uint2* __restrict__ Tp, bool first_half) {
    uint32_t sw[8][8];
#pragma unroll
    for (int j = 0; j < 8; j++) { ldsm_x4(&sw[j][0], ub + o0 + j * 256); ldsm_x4(&sw[j][4], ub + o1 + j * 256); }
#pragma unroll
    for (int M = 0; M < 4; M++) {
#pragma unroll
        for (int i = 0; i < 4; i++) {
            const uint2 hi = Tp[128 * M + 16 * i], lo = Tp[128 * M + 16 * i - 8];
#pragma unroll
            for (int j = FULL ? 0 : M; j < 8; j++) mma_bf16(acc[j], hi.x, hi.y, lo.x, lo.y, sw[(j - M) & 7][2 * i], sw[(j - M) & 7][2 * i + 1]);
        }
        if (FULL) {
            ldsm_x4(&sw[7 - M][0], ub + o0 - (M + 1) * 256);
            if (M < 3) ldsm_x4(&sw[7 - M][4], ub + o1 - (M + 1) * 256);
        }
    }
    if (first_half) {
        const uint2 hi = Tp[512], lo = Tp[504];
#pragma unroll
        for (int j = FULL ? 0 : 4; j < 8; j++) mma_bf16(acc[j], hi.x, hi.y, lo.x, lo.y, sw[(j - 4) & 7][0], sw[(j - 4) & 7][1]);
    }
}
__device__ __forceinline__ void mbar_init(uint32_t bar, int count) { asm volatile("mbarrier.init.shared::cta.b64 [%0], %1;" ::"r"(bar), "r"(count)); }
__device__ __forceinline__ void mbar_arrive(uint32_t bar) { asm volatile("mbarrier.arrive.shared::cta.b64 _, [%0];" ::"r"(bar) : "memory"); }
__device__ __forceinline__ void mbar_wait(uint32_t bar, uint32_t parity) {
    asm volatile("{\n.reg .pred p;\nWAIT_LOOP:\n"
                 "mbarrier.try_wait.parity.shared::cta.b64 p, [%0], %1;\n"
                 "@p bra.uni WAIT_DONE;\nbra.uni WAIT_LOOP;\nWAIT_DONE:\n}" ::"r"(bar), "r"(parity) : "memory");
}

__device__ __forceinline__ void mbar_expect_tx(uint32_t bar, uint32_t bytes) {
    asm volatile("mbarrier.arrive.expect_tx.shared::cta.b64 _, [%0], %1;" ::"r"(bar), "r"(bytes) : "memory");
}
__device__ __forceinline__ void tma_load_2d(uint32_t dst, const void* tmap, int c0, int c1, uint32_t bar) {
    asm volatile("cp.async.bulk.tensor.2d.shared::cluster.global.mbarrier::complete_tx::bytes [%0], [%1, {%3, %4}], [%2];"
                 ::"r"(dst), "l"(tmap), "r"(bar), "r"(c0), "r"(c1) : "memory");
}
__device__ __forceinline__ void fence_async_smem() { asm volatile("fence.proxy.async.shared::cta;" ::: "memory"); }
__device__ __forceinline__ void bulk_load(uint32_t dst, const void* src, uint32_t bytes, uint32_t bar) {
    asm volatile("cp.async.bulk.shared::cluster.global.mbarrier::complete_tx::bytes [%0], [%1], %2, [%3];"
                 ::"r"(dst), "l"(src), "r"(bytes), "r"(bar) : "memory");
}
__device__ __forceinline__ void tma_store_2d(const void* tmap, int c0, int c1, uint32_t src) {
    asm volatile("cp.async.bulk.tensor.2d.global.shared::cta.bulk_group [%0, {%1, %2}], [%3];" ::"l"(tmap), "r"(c0), "r"(c1), "r"(src) : "memory");
    asm volatile("cp.async.bulk.commit_group;" ::: "memory");
    asm volatile("cp.async.bulk.wait_group.read 0;" ::: "memory");
}
__device__ __forceinline__ void stsm_x4(uint32_t addr, uint32_t r0, uint32_t r1, uint32_t r2, uint32_t r3) {
    asm volatile("stmatrix.sync.aligned.m8n8.x4.shared.b16 [%0], {%1,%2,%3,%4};" ::"r"(addr), "r"(r0), "r"(r1), "r"(r2), "r"(r3) : "memory");
}
__device__ __forceinline__ void stsm_x4_t(uint32_t addr, uint32_t r0, uint32_t r1, uint32_t r2, uint32_t r3) {
    asm volatile("stmatrix.sync.aligned.m8n8.x4.trans.shared.b16 [%0], {%1,%2,%3,%4};" ::"r"(addr), "r"(r0), "r"(r1), "r"(r2), "r"(r3) : "memory");
}
__device__ __forceinline__ void prefetch_tmap(const void* tmap) { asm volatile("prefetch.tensormap [%0];" ::"l"(tmap) : "memory"); }

__device__ __forceinline__ uint32_t fin2(uint32_t x, uint32_t y, uint32_t u, uint32_t dk) {
    typedef __nv_bfloat162 b2;
    const b2 r = __hadd2_rn(*reinterpret_cast<const b2*>(&x), __hadd2_rn(*reinterpret_cast<const b2*>(&y),
                            __hmul2_rn(*reinterpret_cast<const b2*>(&u), *reinterpret_cast<const b2*>(&dk))));
    return *reinterpret_cast<const uint32_t*>(&r);
}
__global__ void __launch_bounds__(CV_THREADS, 1) conv_kernel(const bf16* __restrict__ Dskip, int layer, const __grid_constant__ CUtensorMap tmOut) {
    extern __shared__ __align__(128) unsigned char sm[];
    SPAN(3 + 4 * layer, 0);
    bf16* Us = reinterpret_cast<bf16*>(sm + CV_SM_U);
    bf16* Xs = reinterpret_cast<bf16*>(sm + CV_SM_X);
    bf16* Ys = reinterpret_cast<bf16*>(sm + CV_SM_Y);
    const int tid = threadIdx.x, lane = tid & 31, warp = __shfl_sync(~0u, tid >> 5, 0);
    const int d0 = blockIdx.x * CV_CPB, tile = blockIdx.x; (void)tile;
    TSTAMP1X(9, 256);
    unsigned short dskr;
    asm volatile("ld.global.nc.u16 %0, [%1];" : "=h"(dskr) : "l"(Dskip + d0 + min(lane, CV_CPB - 1)));
    if (tid >= 256) {
        const int t2 = tid - 256;
        if (t2 == 0) {
            mbar_init(smem_u32(sm + CV_SM_CNT) + 104, 1);
            asm volatile("fence.mbarrier_init.release.cluster;" ::: "memory");
            mbar_expect_tx(smem_u32(sm + CV_SM_CNT) + 104, CV_CPB * 2048);
            bulk_load(smem_u32(sm + CV_SM_O), g_tap + d0 * 128, CV_CPB * 2048, smem_u32(sm + CV_SM_CNT) + 104);
        } else if (lane == 0) {
            mbar_init(smem_u32(sm + CV_SM_CNT) + 16 * (warp - 9), warp == 15 ? 16 : 1);
            if (warp < 15) mbar_init(smem_u32(sm + CV_SM_CNT) + 16 * (warp - 9) + 8, 1);
            else if (layer) prefetch_tmap(&tmOut);
        }
        if (t2 < 149) {
            const int k = t2;
            const int off = k < 18 ? BX_5 + 8 * k : k < 37 ? BX_3 + 8 * (k - 18) : k < 69 ? BX_9 + 8 * (k - 37) : k < 101 ? BX_7 + 8 * (k - 69)
                          : k < 133 ? 8 * (k - 101) : (UPADF + SEQ) * 2 + 8 * (k - 133);
#pragma unroll
            for (int c = 0; c < CV_CPB; c++) *reinterpret_cast<uint2*>(sm + (k < 101 ? CV_SM_B + c * BX_LEN : CV_SM_U + c * ULEN * 2) + off) = make_uint2(0, 0);
        }
        asm volatile("bar.sync 1, 256;" ::: "memory");
        TSTAMP1X(10, 256);
        mbar_wait(smem_u32(sm + CV_SM_CNT) + 104, 0);
        TSTAMP1X(11, 256);
#pragma unroll 1
        for (int r = t2; r < 392; r += 256) {
            const bool dd = r < 272, cc = r >= 368;
            const uint32_t* E2 = reinterpret_cast<const uint32_t*>(sm + CV_SM_O) + (dd ? r + 3 : r < 320 ? 301 + 2 * (r - 272) : cc ? 417 : 401 + 2 * (r - 320));
            const uint32_t* E3 = E2 + (dd ? 4 : cc ? 0 : 1);
            const uint32_t s0 = !cc ? 0x7610u : r == 382 ? 0x1044u : 0x4444u, s1 = !cc ? 0x7610u : r == 378 ? 0x1044u : 0x4444u;
            const uint32_t s2 = !cc ? 0x1032u : r == 381 ? 0x4410u : 0x4444u, s3 = !cc ? 0x1032u : r == 377 ? 0x4410u : 0x4444u;
            uint32_t w[CV_CPB][4];
#pragma unroll
            for (int c = 0; c < CV_CPB; c++) { w[c][0] = E2[512 * c]; w[c][1] = E2[512 * c + 1]; w[c][2] = E3[512 * c]; w[c][3] = E3[512 * c + 1]; }
#pragma unroll
            for (int c = 0; c < CV_CPB; c++) {
                const uint32_t a = __byte_perm(w[c][3], w[c][2], s1), b = __byte_perm(w[c][1], w[c][0], s2);
                *reinterpret_cast<uint4*>(sm + CV_SM_T + c * TAPB + r * 16) =
                    make_uint4(__byte_perm(w[c][1], w[c][0], s0), dd || cc ? a : b, dd || cc ? b : a, __byte_perm(w[c][3], w[c][2], s3));
            }
        }
        TSTAMP1X(12, 256);
        if (layer == 0) {
#pragma unroll
            for (int c = 0; c < CV_CPB; c++) reinterpret_cast<uint4*>(g_yT + (size_t)(d0 + c) * XCP)[t2] = make_uint4(~0u, ~0u, ~0u, ~0u);
        }
        pdl_sync();
        if (layer && blockIdx.x == 0 && t2 == 0) g_epoch = ld_epoch();
    } else {
        const uint4* ppv = reinterpret_cast<const uint4*>(g_piv + layer * SEQ) + tid;
        const float4* psv = reinterpret_cast<const float4*>(g_sum + layer * SEQ) + tid;
        const uint4* pxv = reinterpret_cast<const uint4*>(g_x1T + (size_t)d0 * XCP) + tid;
        asm volatile("" : "+l"(ppv), "+l"(psv), "+l"(pxv));
        pdl_sync();
        SPAN(3 + 4 * layer, 1);
        TSTAMP(0);
        if (threadIdx.x == 0) { GSTAMP(g_tim, 15); }
        float4 sv[4];
#pragma unroll
        for (int k = 0; k < 4; k++) sv[k] = __ldcg(psv + 256 * k);
        const uint4 pv = __ldcg(ppv);
        uint4 xv[CV_CPB];
#pragma unroll
        for (int c = 0; c < CV_CPB; c++) xv[c] = __ldcg(pxv + c * (XCP / 8));
        uint32_t mw[4];
        float rs[8];
#pragma unroll
        for (int k = 0; k < 4; k++) {
            const uint32_t pw = k == 0 ? pv.x : k == 1 ? pv.y : k == 2 ? pv.z : pv.w;
            const float d0_ = sv[k].x * (1.0f / DM), d1_ = sv[k].z * (1.0f / DM);
            mw[k] = pack2(__uint_as_float(pw << 16) + d0_, __uint_as_float(pw & 0xffff0000u) + d1_);
            const uint32_t vr = pack2(fmaxf(fmaf(-d0_, d0_, sv[k].y * (1.0f / DM)), 0.f), fmaxf(fmaf(-d1_, d1_, sv[k].w * (1.0f / DM)), 0.f));
            const uint32_t ve = pack2(__uint_as_float(vr << 16) + 1e-5f, __uint_as_float(vr & 0xffff0000u) + 1e-5f);
            const uint32_t sd = pack2(sqrt_apx(__uint_as_float(ve << 16)), sqrt_apx(__uint_as_float(ve & 0xffff0000u)));
            rs[2 * k] = rcp_apx(__uint_as_float(sd << 16)); rs[2 * k + 1] = rcp_apx(__uint_as_float(sd & 0xffff0000u));
        }
        if (rs[0] != 123.f) TSTAMP(13);
        const int ch = tid + UPADF / 8, pch = ch ^ ((ch >> 3) & 1);
#pragma unroll
        for (int c = 0; c < CV_CPB; c++) {
            *reinterpret_cast<uint4*>(Xs + c * XLEN + tid * 8) = xv[c];
            *reinterpret_cast<uint4*>(Us + c * ULEN + pch * 8) =
                make_uint4(ln2(xv[c].x, mw[0], rs[0], rs[1]), ln2(xv[c].y, mw[1], rs[2], rs[3]), ln2(xv[c].z, mw[2], rs[4], rs[5]), ln2(xv[c].w, mw[3], rs[6], rs[7]));
        }
    }
    __syncthreads();
    TSTAMP(1);
    const uint32_t rstart = warp < 8 ? (warp < 4 ? 0x02000000u : 0x06040000u) : (warp < 12 ? 0x0C0B0A08u : 0x1E1D150Fu);
    const uint32_t rcount = warp < 8 ? 0x02020000u : (warp < 12 ? 0x03010102u : 0x01010806u);
#pragma unroll 1
    for (int rd = (rstart >> (8 * (warp & 3))) & 0xff, re = rd + ((rcount >> (8 * (warp & 3))) & 0xff); rd < re; rd++) {
        const int i = 32 * rd + lane;
        if (i < CV_CPB * 193) {
            const int c = i / 193, chunk = i - c * 193 - 1, ch = chunk + UPADF / 8;
            const bf16* uc = Us + c * ULEN;
            const uint4 o = *reinterpret_cast<const uint4*>(uc + (ch ^ ((ch >> 3) & 1)) * 8);
            const uint2 lo = *reinterpret_cast<const uint2*>(uc + ((ch - 1) ^ (((ch - 1) >> 3) & 1)) * 8 + 4);
            const uint2 hi = *reinterpret_cast<const uint2*>(uc + ((ch + 1) ^ (((ch + 1) >> 3) & 1)) * 8);
            const uint32_t w[8] = {lo.x, lo.y, o.x, o.y, o.z, o.w, hi.x, hi.y};
            float v[16], b[8];
#pragma unroll
            for (int k = 0; k < 8; k++) { v[2 * k] = __uint_as_float(w[k] << 16); v[2 * k + 1] = __uint_as_float(w[k] & 0xffff0000u); }
            unsigned char* bx = sm + CV_SM_B + c * BX_LEN + chunk * 16;
#pragma unroll
            for (int k = 0; k < 8; k++) b[k] = v[k + 4] + (v[k + 3] + v[k + 5]);
            *reinterpret_cast<uint2*>(bx + BX_3 + 168) = make_uint2(pack2(b[0], b[1]), pack2(b[2], b[3]));
            *reinterpret_cast<uint2*>(bx + BX_3 + 176) = make_uint2(pack2(b[4], b[5]), pack2(b[6], b[7]));
#pragma unroll
            for (int k = 0; k < 8; k++) b[k] += v[k + 2] + v[k + 6];
            *reinterpret_cast<uint4*>(bx + BX_5 + 160) = make_uint4(pack2(b[0], b[1]), pack2(b[2], b[3]), pack2(b[4], b[5]), pack2(b[6], b[7]));
            if (chunk < 128) {
#pragma unroll
                for (int k = 0; k < 8; k++) b[k] += v[k + 1] + v[k + 7];
                *reinterpret_cast<uint4*>(bx + BX_7 + 272) = make_uint4(pack2(b[0], b[1]), pack2(b[2], b[3]), pack2(b[4], b[5]), pack2(b[6], b[7]));
#pragma unroll
                for (int k = 0; k < 8; k++) b[k] += v[k] + v[k + 8];
                *reinterpret_cast<uint4*>(bx + BX_9 + 272) = make_uint4(pack2(b[0], b[1]), pack2(b[2], b[3]), pack2(b[4], b[5]), pack2(b[6], b[7]));
            }
        }
    }
    __syncwarp();
    if (lane == 0) mbar_arrive(smem_u32(sm + CV_SM_CNT) + 96);
    TSTAMP(2);
    {
        const int g = lane >> 2, ti = lane & 3;
        const int e = g - 2 * ti;
        uint32_t lds_off[4];
        uint32_t off2, off3, offc;
        {
            const int mat = lane >> 3, r = lane & 7;
#pragma unroll
            for (int pr = 0; pr < 4; pr++) {
                const int iw = 2 * pr + (mat >> 1), half = mat & 1;
                const int chunk = (UPADF - 16 * iw + 16 * r + 8 * half) >> 3;
                lds_off[pr] = (uint32_t)((chunk ^ ((chunk >> 3) & 1)) * 16);
            }
            const int j2 = 13 + r + 8 * (mat >> 1), j3 = j2 + 2, i0 = 8 * (mat & 1);
            off2 = (j2 & 1) ? BX_3 + (4 * j2 + i0 + 84) * 2 : BX_5 + (4 * j2 + i0 + 80) * 2;
            off3 = ((j3 & 1) ? BX_7 : BX_9) + (8 * j3 + i0 + 136) * 2;
            const int cc = (UPADF + 16 * (r + (mat >> 1)) + i0) >> 3;
            offc = (uint32_t)((cc ^ ((cc >> 3) & 1)) * 16);
        }
        const uint32_t rtab = warp < 8 ? (warp < 4 ? 0x0B090200u : 0x0C0A0301u) : (warp < 12 ? 0x13111008u : 0x1412241Cu);
        const int rl = (rtab >> (8 * (warp & 3))) & 0xff, type = rl >> 3, c = rl & 7;
        const int H = (type == 1 || type == 2) ? 1 : 0, T0 = 8 * H;
        const uint2* Tc = reinterpret_cast<const uint2*>(sm + CV_SM_T + c * TAPB) + TPAD + e;
        const uint32_t ubase = smem_u32(Us + c * ULEN);
        const uint32_t bbase = smem_u32(sm + CV_SM_B + c * BX_LEN);
        float acc[8][4];
#pragma unroll
        for (int j = 0; j < 8; j++)
#pragma unroll
            for (int k = 0; k < 4; k++) acc[j][k] = 0.f;
#pragma unroll 1
        for (int pass = (type == 2 || type == 4) ? 1 : 0; pass < ((type == 1 || type == 3) ? 1 : 2); pass++) {
            const uint32_t o0 = pass ? lds_off[2] : lds_off[0], o1 = pass ? lds_off[3] : lds_off[1];
            if (H) direct_pass<true>(acc, ubase + T0 * 256, o0, o1, Tc + 64 * pass, pass == 0);
            else direct_pass<false>(acc, ubase, o0, o1, Tc + 64 * pass, pass == 0);
        }
        TSTAMP(6);
        mbar_wait(smem_u32(sm + CV_SM_CNT) + 96, 0);
        if (type != 1 && type != 4) {
            const uint32_t* w2 = reinterpret_cast<const uint32_t*>(sm + CV_SM_T + c * TAPB + TAP_W2) + (115 - 96) + 4 * g - 2 * ti;
            uint32_t f[10][2];
#pragma unroll
            for (int k = 0; k < 10; k++) { f[k][0] = w2[16 * k]; f[k][1] = w2[16 * k - 8]; }
            const uint32_t ab = bbase + off2 + (2 * T0 + 6) * 128;
            const int kmax = H ? 23 : 8;
            uint32_t a[3][4];
            ldsm_x4_t(a[0], ab);
            ldsm_x4_t(a[1], ab - 128);
#pragma unroll
            for (int kp = 0; kp < 24; kp++) {
                if (kp > kmax) break;
                if (kp < 22) ldsm_x4_t(a[(kp + 2) % 3], ab - min(kp + 2, kmax) * 128);
#pragma unroll
                for (int j = 0; j < 8; j++) {
                    const int ee = 2 * j - 14 + kp;
                    if (ee >= 0 && ee <= 9) mma_bf16(acc[j], a[kp % 3][0], a[kp % 3][1], a[kp % 3][2], a[kp % 3][3], f[ee][0], f[ee][1]);
                }
            }
        }
        TSTAMP(7);
        if (type != 2 && type != 4) {
            const uint32_t* w3 = reinterpret_cast<const uint32_t*>(sm + CV_SM_T + c * TAPB + TAP_W3) + (129 - 96) + 2 * (g - ti);
            uint32_t f[9][2];
#pragma unroll
            for (int k = 0; k < 9; k++) { f[k][0] = w3[16 * k]; f[k][1] = w3[16 * k - 8]; }
            const uint32_t ab = bbase + off3 + (T0 - 2) * 256;
            uint32_t a[3][4];
            ldsm_x4_t(a[0], ab);
            ldsm_x4_t(a[1], ab - H * 256);
#pragma unroll
            for (int kp = 0; kp < 9; kp++) {
                if (kp > T0) break;
                if (kp < 7) ldsm_x4_t(a[(kp + 2) % 3], ab - min(kp + 2, T0) * 256);
#pragma unroll
                for (int j = 0; j < 8; j++) {
                    const int dl = j - 7 + kp;
                    if (dl >= 0 && dl <= 8) mma_bf16(acc[j], a[kp % 3][0], a[kp % 3][1], a[kp % 3][2], a[kp % 3][3], f[dl][0], f[dl][1]);
                }
            }
            const uint2* Dc = reinterpret_cast<const uint2*>(sm + CV_SM_T + c * TAPB + TAP_C) + e;
            const uint2 h63 = Dc[16], h64 = Dc[32], l63 = Dc[8], l64 = Dc[24];
#pragma unroll
            for (int j = 0; j < 8; j++)
                if (j == 7 || H) {
                    uint32_t bq[4];
                    ldsm_x4(bq, ubase + offc + (T0 + j - 8) * 256);
                    mma_bf16(acc[j], h64.x, h64.y, l64.x, l64.y, bq[0], bq[1]);
                    mma_bf16(acc[j], h63.x, h63.y, l63.x, l63.y, bq[2], bq[3]);
                }
        }
        TSTAMP(8);
        const bool hi_half = (type == 2 || type == 4);
        if (type != 0) {
            const int pair = H ? c : 5;
            float4* give = reinterpret_cast<float4*>(sm + CV_SM_P + pair * 4096 + (hi_half ? 2048 : 0)) + lane;
            const float4* take = reinterpret_cast<const float4*>(sm + CV_SM_P + pair * 4096 + (hi_half ? 0 : 2048)) + lane;
            const uint32_t pb = smem_u32(sm + CV_SM_CNT) + pair * 16;
#pragma unroll
            for (int j = 0; j < 4; j++)
                give[32 * j] = hi_half ? make_float4(acc[j][0], acc[j][1], acc[j][2], acc[j][3]) : make_float4(acc[j + 4][0], acc[j + 4][1], acc[j + 4][2], acc[j + 4][3]);
            __syncwarp();
            if (lane == 0) mbar_arrive(pb + (hi_half ? 8 : 0));
            mbar_wait(pb + (hi_half ? 0 : 8), 0);
#pragma unroll
            for (int j = 0; j < 4; j++) {
                const float4 v = take[32 * j];
                acc[j][0] = (hi_half ? acc[j + 4][0] : acc[j][0]) + v.x; acc[j][1] = (hi_half ? acc[j + 4][1] : acc[j][1]) + v.y;
                acc[j][2] = (hi_half ? acc[j + 4][2] : acc[j][2]) + v.z; acc[j][3] = (hi_half ? acc[j + 4][3] : acc[j][3]) + v.w;
            }
        }
        const uint32_t dk = __shfl_sync(~0u, (uint32_t)dskr, c) * 0x10001u;
#pragma unroll 1
        for (int rnd = 0; rnd < (type == 0 ? 2 : 1); rnd++) {
            const int Q = 2 * H + (hi_half ? 1 : rnd);
            if (rnd) {
#pragma unroll
                for (int j = 0; j < 4; j++)
#pragma unroll
                    for (int k = 0; k < 4; k++) acc[j][k] = acc[j + 4][k];
            }
            const uint32_t ya = smem_u32(Ys + c * XLEN) + (128 * (4 * Q + (lane >> 4)) + 16 * (lane & 7) + 8 * ((lane >> 3) & 1)) * 2;
#pragma unroll
            for (int j = 0; j < 4; j += 2)
                asm volatile("stmatrix.sync.aligned.m8n8.x4.trans.shared.b16 [%0], {%1,%2,%3,%4};" ::"r"(ya + j * 256),
                             "r"(pack2(acc[j][0], acc[j][1])), "r"(pack2(acc[j][2], acc[j][3])),
                             "r"(pack2(acc[j + 1][0], acc[j + 1][1])), "r"(pack2(acc[j + 1][2], acc[j + 1][3])) : "memory");
            __syncwarp();
            uint4 yv[2], xv[2], uv[2];
#pragma unroll
            for (int k = 0; k < 2; k++) {
                const int t = 512 * Q + 256 * k + 8 * lane, cu = (t + UPADF) >> 3;
                yv[k] = *reinterpret_cast<const uint4*>(Ys + c * XLEN + t);
                xv[k] = *reinterpret_cast<const uint4*>(Xs + c * XLEN + t);
                uv[k] = *reinterpret_cast<const uint4*>(Us + c * ULEN + (cu ^ ((cu >> 3) & 1)) * 8);
            }
#pragma unroll
            for (int k = 0; k < 2; k++)
                asm volatile("st.relaxed.gpu.global.v4.u32 [%0], {%1,%2,%3,%4};" ::"l"((layer ? g_yT : g_xcT) + (size_t)(d0 + c) * XCP + 512 * Q + 256 * k + 8 * lane),
                             "r"(fin2(xv[k].x, yv[k].x, uv[k].x, dk)), "r"(fin2(xv[k].y, yv[k].y, uv[k].y, dk)), "r"(fin2(xv[k].z, yv[k].z, uv[k].z, dk)), "r"(fin2(xv[k].w, yv[k].w, uv[k].w, dk)) : "memory");
        }
        TSTAMP(4);
        if (layer == 1) {
            const int mb = blockIdx.x >> 3, cg = blockIdx.x & 7;
            const bf16* src = g_yT + (size_t)(cg * 80 + (tid >> 4)) * XCP + mb * 128 + (tid & 15) * 8;
            uint32_t v[3][4];
            __syncthreads();
            TSTAMP(5);
            uint32_t todo = warp < 8 ? 7 : 3;
#pragma unroll 1
            for (int it = 0; it < SPIN_MAX; it++) {
#pragma unroll
                for (int k = 0; k < 3; k++)
                    if (todo >> k & 1)
                        asm volatile("ld.relaxed.gpu.global.v4.u32 {%0,%1,%2,%3}, [%4];" : "=r"(v[k][0]), "=r"(v[k][1]), "=r"(v[k][2]), "=r"(v[k][3]) : "l"(src + k * (32 * XCP)) : "memory");
#pragma unroll
                for (int k = 0; k < 3; k++)
                    if ((todo >> k & 1) && v[k][0] != ~0u && v[k][1] != ~0u && v[k][2] != ~0u && v[k][3] != ~0u) {
                        *reinterpret_cast<uint4*>(sm + (32 * k + (tid >> 4)) * 272 + (tid & 15) * 16) = make_uint4(v[k][0], v[k][1], v[k][2], v[k][3]);
                        todo ^= 1u << k;
                    }
                if (!todo) break;
                __nanosleep(CV_SLEEP);
            }
            __syncthreads();
            uint32_t w[12];
#pragma unroll
            for (int k = 0; k < 3; k++) ldsm_x4(&w[4 * k], smem_u32(sm) + min(32 * k + lane, 79) * 272 + warp * 16);
            const uint32_t ot = smem_u32(sm + CV_SM_O) + warp * 1280, oa = ot + (lane & 7) * 160 + (lane >> 3) * 16;
            stsm_x4_t(oa, w[0], w[1], w[2], w[3]);
            stsm_x4_t(oa + 64, w[4], w[5], w[6], w[7]);
            asm volatile("stmatrix.sync.aligned.m8n8.x2.trans.shared.b16 [%0], {%1,%2};" ::"r"(oa + 128), "r"(w[8]), "r"(w[9]) : "memory");
            fence_async_smem();
            __syncwarp();
            if (lane == 0) tma_store_2d(&tmOut, cg * 80, mb * 128 + 8 * warp, ot);
        }
    }
    TSTAMP(3);
    GSTAMP(g_tim, 14);
    SPAN(3 + 4 * layer, 3);
}

__device__ __forceinline__ void wgmma_fence() { asm volatile("wgmma.fence.sync.aligned;" ::: "memory"); }
__device__ __forceinline__ void wgmma_commit() { asm volatile("wgmma.commit_group.sync.aligned;" ::: "memory"); }
template <int N> __device__ __forceinline__ void wgmma_wait() { asm volatile("wgmma.wait_group.sync.aligned %0;" ::"n"(N) : "memory"); }
__device__ __forceinline__ uint64_t make_desc(uint32_t addr, uint32_t lbo, uint32_t sbo, uint32_t mode) {
    return (uint64_t)((addr & 0x3FFFF) >> 4) | ((uint64_t)(lbo >> 4) << 16) | ((uint64_t)(sbo >> 4) << 32) | ((uint64_t)mode << 62);
}
template <int TA, int TB>
__device__ __forceinline__ void wgmma_n240(float (&d)[120], uint64_t da, uint64_t db) {
    asm volatile("wgmma.mma_async.sync.aligned.m64n240k16.f32.bf16.bf16 {%0,%1,%2,%3,%4,%5,%6,%7,%8,%9,%10,%11,%12,%13,%14,%15,%16,%17,%18,%19,%20,%21,%22,%23,%24,%25,%26,%27,%28,%29,%30,%31,%32,%33,%34,%35,%36,%37,%38,%39,%40,%41,%42,%43,%44,%45,%46,%47,%48,%49,%50,%51,%52,%53,%54,%55,%56,%57,%58,%59,%60,%61,%62,%63,%64,%65,%66,%67,%68,%69,%70,%71,%72,%73,%74,%75,%76,%77,%78,%79,%80,%81,%82,%83,%84,%85,%86,%87,%88,%89,%90,%91,%92,%93,%94,%95,%96,%97,%98,%99,%100,%101,%102,%103,%104,%105,%106,%107,%108,%109,%110,%111,%112,%113,%114,%115,%116,%117,%118,%119}, %120, %121, 1, 1, 1, %122, %123;"
                 : "+f"(d[0]), "+f"(d[1]), "+f"(d[2]), "+f"(d[3]), "+f"(d[4]), "+f"(d[5]), "+f"(d[6]), "+f"(d[7]), "+f"(d[8]), "+f"(d[9]), "+f"(d[10]), "+f"(d[11]), "+f"(d[12]), "+f"(d[13]), "+f"(d[14]), "+f"(d[15]), "+f"(d[16]), "+f"(d[17]), "+f"(d[18]), "+f"(d[19]), "+f"(d[20]), "+f"(d[21]), "+f"(d[22]), "+f"(d[23]), "+f"(d[24]), "+f"(d[25]), "+f"(d[26]), "+f"(d[27]), "+f"(d[28]), "+f"(d[29]), "+f"(d[30]), "+f"(d[31]), "+f"(d[32]), "+f"(d[33]), "+f"(d[34]), "+f"(d[35]), "+f"(d[36]), "+f"(d[37]), "+f"(d[38]), "+f"(d[39]), "+f"(d[40]), "+f"(d[41]), "+f"(d[42]), "+f"(d[43]), "+f"(d[44]), "+f"(d[45]), "+f"(d[46]), "+f"(d[47]), "+f"(d[48]), "+f"(d[49]), "+f"(d[50]), "+f"(d[51]), "+f"(d[52]), "+f"(d[53]), "+f"(d[54]), "+f"(d[55]), "+f"(d[56]), "+f"(d[57]), "+f"(d[58]), "+f"(d[59]), "+f"(d[60]), "+f"(d[61]), "+f"(d[62]), "+f"(d[63]), "+f"(d[64]), "+f"(d[65]), "+f"(d[66]), "+f"(d[67]), "+f"(d[68]), "+f"(d[69]), "+f"(d[70]), "+f"(d[71]), "+f"(d[72]), "+f"(d[73]), "+f"(d[74]), "+f"(d[75]), "+f"(d[76]), "+f"(d[77]), "+f"(d[78]), "+f"(d[79]), "+f"(d[80]), "+f"(d[81]), "+f"(d[82]), "+f"(d[83]), "+f"(d[84]), "+f"(d[85]), "+f"(d[86]), "+f"(d[87]), "+f"(d[88]), "+f"(d[89]), "+f"(d[90]), "+f"(d[91]), "+f"(d[92]), "+f"(d[93]), "+f"(d[94]), "+f"(d[95]), "+f"(d[96]), "+f"(d[97]), "+f"(d[98]), "+f"(d[99]), "+f"(d[100]), "+f"(d[101]), "+f"(d[102]), "+f"(d[103]), "+f"(d[104]), "+f"(d[105]), "+f"(d[106]), "+f"(d[107]), "+f"(d[108]), "+f"(d[109]), "+f"(d[110]), "+f"(d[111]), "+f"(d[112]), "+f"(d[113]), "+f"(d[114]), "+f"(d[115]), "+f"(d[116]), "+f"(d[117]), "+f"(d[118]), "+f"(d[119])
                 : "l"(da), "l"(db), "n"(TA), "n"(TB));
}

template <int TA, int TB>
__device__ __forceinline__ void wgmma_n80(float (&d)[40], uint64_t da, uint64_t db) {
    asm volatile("wgmma.mma_async.sync.aligned.m64n80k16.f32.bf16.bf16 {%0,%1,%2,%3,%4,%5,%6,%7,%8,%9,%10,%11,%12,%13,%14,%15,%16,%17,%18,%19,%20,%21,%22,%23,%24,%25,%26,%27,%28,%29,%30,%31,%32,%33,%34,%35,%36,%37,%38,%39}, %40, %41, 1, 1, 1, %42, %43;"
                 : "+f"(d[0]), "+f"(d[1]), "+f"(d[2]), "+f"(d[3]), "+f"(d[4]), "+f"(d[5]), "+f"(d[6]), "+f"(d[7]), "+f"(d[8]), "+f"(d[9]), "+f"(d[10]), "+f"(d[11]), "+f"(d[12]), "+f"(d[13]), "+f"(d[14]), "+f"(d[15]), "+f"(d[16]), "+f"(d[17]), "+f"(d[18]), "+f"(d[19]), "+f"(d[20]), "+f"(d[21]), "+f"(d[22]), "+f"(d[23]), "+f"(d[24]), "+f"(d[25]), "+f"(d[26]), "+f"(d[27]), "+f"(d[28]), "+f"(d[29]), "+f"(d[30]), "+f"(d[31]), "+f"(d[32]), "+f"(d[33]), "+f"(d[34]), "+f"(d[35]), "+f"(d[36]), "+f"(d[37]), "+f"(d[38]), "+f"(d[39])
                 : "l"(da), "l"(db), "n"(TA), "n"(TB));
}

constexpr int A1_THREADS = 384;
constexpr int A1_NST = 4;
#define A1_PRE0 2
#define A1_SDELAY 1
#define A1_SKEW 8
#define A1_PRE1 1
constexpr int A1_STAGE = 16384 + WQ_STAGE;
constexpr int A1_KVP = 336;
constexpr int A1_SM_KV = 2 * A1_STAGE;
constexpr int A1_SM_O = A1_SM_KV + 144 * A1_KVP;
constexpr int A1_SM_R = A1_NST * A1_STAGE;
constexpr int A1_SM_BAR = A1_SM_R + 20480;
constexpr int A1_SM_CS = A1_SM_BAR + 256;
constexpr int A1_SM_RS = A1_SM_CS + 1024;
constexpr int A1_SMEM = A1_SM_RS + 1024 + 1024;
static_assert(A1_SM_O % 128 == 0 && A1_SM_O + 20480 <= A1_SM_R, "layout");

template <int L>
__device__ __forceinline__ void a1_mainloop(float (&acc)[120], uint32_t sbase, uint32_t bars, int wg, int tile) {
    constexpr int layer = L; (void)layer;
    const uint64_t da0 = L ? make_desc(sbase + wg * 8192, 8192, 1024, 1) : make_desc(sbase + wg * 8192, 16, 1024, 1), db0 = make_desc(sbase + 16384, 16, 1024, 1);
#pragma unroll 1
    for (int t = 0; t < 10; t++) {
        const int st = t % A1_NST;
        mbar_wait(bars + 8 * st, (t / A1_NST) & 1);
        if (t == A1_SKEW && wg == 0) mbar_wait(bars + 160, 0);
        TSTAMP3(1 + t);
        wgmma_fence();
#pragma unroll
        for (int kk = 0; kk < 4; kk++) wgmma_n240<L, 0>(acc, da0 + (uint32_t)(st * (A1_STAGE / 16) + kk * (L ? 128 : 2)), db0 + (uint32_t)(st * (A1_STAGE / 16) + kk * 2));
        wgmma_commit();
        if (t == 9 && threadIdx.x == 128) { mbar_arrive(bars + 160); mbar_arrive(bars + 144); }
        if (t == A1_SKEW - 1 && wg == 0) wgmma_wait<0>(); else wgmma_wait<1>();
        if (t > 0 && t < 9 && (threadIdx.x & 127) == 0) {
            if (t != A1_SKEW || wg) mbar_arrive(bars + 8 * (A1_NST + (t - 1) % A1_NST));
            if (t == A1_SKEW - 1 && wg == 0) mbar_arrive(bars + 8 * (A1_NST + t % A1_NST));
        }
    }
}

__global__ void __launch_bounds__(A1_THREADS, 1) a1_kernel(const int layer, const bf16* __restrict__ x0, const __grid_constant__ CUtensorMap tmX,
                                                           const __grid_constant__ CUtensorMap tmR, const __grid_constant__ CUtensorMap tmOst) {
    extern __shared__ unsigned char smraw[];
    const uint32_t sbase = (smem_u32(smraw) + 1023) & ~1023u;
    const uint32_t bars = sbase + A1_SM_BAR;
    const uint32_t bar_stat = bars + 64, bar_kv = bars + 72, bar_r = bars + 152;
    const int tid = threadIdx.x, w = __shfl_sync(~0u, tid >> 5, 0), wg = w >> 2;
    const int tile = sm_tile();
    if (tile >= 128) { sm_idle(2 * layer); return; }
    const int mb = (tile >> 2) & 15, hg = 4 * (tile >> 6) + (tile & 3);
    unsigned char* stg = smraw + (sbase - smem_u32(smraw));
    float* cs = reinterpret_cast<float*>(stg + A1_SM_CS);
    float2* rst = reinterpret_cast<float2*>(stg + A1_SM_RS);
    const int pre = layer ? A1_PRE1 : A1_PRE0;
    auto issue_w = [&](int kb) {
        bulk_load(sbase + (kb % A1_NST) * A1_STAGE + 16384, reinterpret_cast<const unsigned char*>(g_wq) + (hg * 10 + kb) * WQ_STAGE, WQ_STAGE, bars + 8 * (kb % A1_NST));
    };
    auto issue_x = [&](int kb) {
        const uint32_t dst = sbase + (kb % A1_NST) * A1_STAGE, full = bars + 8 * (kb % A1_NST);
        if (layer == 0) tma_load_2d(dst, &tmX, kb * 64, mb * 128, full);
        else { tma_load_2d(dst, &tmX, mb * 128, kb * 64, full); tma_load_2d(dst + 8192, &tmX, mb * 128 + 64, kb * 64, full); }
    };
    if (w == 8) {
        if (tid == 256) {
            prefetch_tmap(&tmX);
#pragma unroll
            for (int i = 0; i < A1_NST; i++) { mbar_init(bars + 8 * i, 1); mbar_init(bars + 8 * (A1_NST + i), 2); }
            mbar_init(bar_r, 1);
            asm volatile("fence.mbarrier_init.release.cluster;" ::: "memory");
#pragma unroll
            for (int i = 0; i < A1_NST; i++) mbar_expect_tx(bars + 8 * i, A1_STAGE);
            mbar_expect_tx(bar_r, 20480);
        }
        __syncwarp();
        asm volatile("bar.arrive 0, 384;" ::: "memory");
        if (tid == 256) {
#pragma unroll 1
            for (int kb = 0; kb < pre; kb++) { if (layer) issue_w(kb); else issue_x(kb); }
            pdl_sync();
#pragma unroll 1
            for (int kb = 0; kb < A1_NST; kb++) {
                if (kb == A1_SDELAY && layer) {
                    tma_load_2d(sbase + A1_SM_R, &tmR, mb * 128, hg * 80, bar_r); tma_load_2d(sbase + A1_SM_R + 10240, &tmR, mb * 128 + 64, hg * 80, bar_r);
                }
                if (kb >= pre || layer) issue_x(kb);
                if (kb >= pre || !layer) issue_w(kb);
            }
        }
    } else {
        if (tid == 0) {
            mbar_init(bar_stat, 2);
#pragma unroll
            for (int i = 0; i < 9; i++) mbar_init(bar_kv + 8 * i, i ? 1 : 4);
            mbar_init(bars + 144, 1);
            mbar_init(bars + 160, 1);
            asm volatile("fence.mbarrier_init.release.cluster;" ::: "memory");
        } else if (tid == 320) { prefetch_tmap(&tmR); prefetch_tmap(&tmOst); }
        asm volatile("bar.sync 0, 384;" ::: "memory");
    }
    SPAN(1 + 4 * layer, 0);
    const uint32_t tag = ld_epoch();
    if (tid == 352) sm_started(2 * layer);
    constexpr int on = 1;
    if (wg == 2) {
        if (w == 9) {
        } else if (w == 8) {
            if (tid == 256) {
#pragma unroll 1
                for (int kb = A1_NST; kb < 10; kb++) {
                    mbar_wait(bars + 8 * (A1_NST + kb % A1_NST), ((kb / A1_NST) - 1) & 1);
                    mbar_expect_tx(bars + 8 * (kb % A1_NST), A1_STAGE);
                    issue_x(kb); issue_w(kb);
                }
                TSTAMP1T(6, 256);
            }
            __syncwarp();
        } else {
            const int j = tid - 320;
            if (layer == 0) {
                const uint4* src = reinterpret_cast<const uint4*>(x0 + (size_t)(mb * 128 + hg * 16 + (j >> 2)) * DM);
                uint4 v[20];
#pragma unroll
                for (int k = 0; k < 20; k++) v[k] = __ldg(src + (j & 3) + 4 * k);
                const float p0 = __uint_as_float(__shfl_sync(~0u, v[0].x, j & 28) << 16);
                float s[2] = {0.f, 0.f}, q[2] = {0.f, 0.f};
#pragma unroll
                for (int k = 0; k < 20; k++) {
                    const uint32_t w[4] = {v[k].x, v[k].y, v[k].z, v[k].w};
#pragma unroll
                    for (int i = 0; i < 4; i++) {
                        const float a = __uint_as_float(w[i] << 16) - p0, b = __uint_as_float(w[i] & 0xffff0000u) - p0;
                        s[0] += a; s[1] += b; q[0] = fmaf(a, a, q[0]); q[1] = fmaf(b, b, q[1]);
                    }
                }
                float s0 = s[0] + s[1], q0 = q[0] + q[1];
#pragma unroll
                for (int o = 1; o <= 2; o <<= 1) { s0 += __shfl_xor_sync(~0u, s0, o); q0 += __shfl_xor_sync(~0u, q0, o); }
                if ((j & 3) == 0) {
                    const float d = s0 * (1.0f / DM);
                    const uint32_t ms = pack2(p0 + d, sqrt_apx(rbf(rbf(fmaxf(fmaf(-d, d, q0 * (1.0f / DM)), 0.f)) + 1e-5f)));
                    asm volatile("st.global.cg.u64 [%0], %1;" ::"l"(g_rstat + mb * 128 + hg * 16 + (j >> 2)), "l"(tagw(ms, tag)) : "memory");
                    g_piv[mb * 128 + hg * 16 + (j >> 2)] = __ushort_as_bfloat16((unsigned short)ms);
                }
                pdl_sync();
            }
            if (j < 60) {
                float4 a = make_float4(0.f, 0.f, 0.f, 0.f);
#pragma unroll
                for (int k = 0; k < 10; k++) {
                    const float4 v = __ldcg(reinterpret_cast<const float4*>(g_csp + k * 1920 + hg * 240) + j);
                    a.x += v.x; a.y += v.y; a.z += v.z; a.w += v.w;
                }
                reinterpret_cast<float4*>(cs)[j] = a;
            }
            if (layer == 0) {
                ulonglong2 v;
#pragma unroll 1
                for (int it = 0; it < SPIN_MAX; it++) {
                    v = ld_tag2(reinterpret_cast<const ulonglong2*>(g_rstat + mb * 128) + j);
                    if (tag_ok(v, tag)) break;
                    __nanosleep(100);
                }
                *reinterpret_cast<float4*>(rst + 2 * j) = make_float4(__uint_as_float((uint32_t)v.x << 16), rcp_apx(__uint_as_float((uint32_t)v.x & 0xffff0000u)),
                                                                      __uint_as_float((uint32_t)v.y << 16), rcp_apx(__uint_as_float((uint32_t)v.y & 0xffff0000u)));
            } else {
                const int ch = j & 7, kg = (j >> 3) & 3;
                const unsigned char* src = stg + A1_SM_R + (j >> 5) * 10240;
                mbar_wait(bar_r, 0);
                uint4 v[20];
#pragma unroll
                for (int k = 0; k < 20; k++) v[k] = *reinterpret_cast<const uint4*>(src + (4 * k + kg) * 128 + ((ch ^ ((4 * k + kg) & 7)) << 4));
                const uint4 pv = *reinterpret_cast<const uint4*>(src + (ch << 4));
                float s[8], q[8], p0[8] = {__uint_as_float(pv.x << 16), __uint_as_float(pv.x & 0xffff0000u), __uint_as_float(pv.y << 16), __uint_as_float(pv.y & 0xffff0000u),
                                           __uint_as_float(pv.z << 16), __uint_as_float(pv.z & 0xffff0000u), __uint_as_float(pv.w << 16), __uint_as_float(pv.w & 0xffff0000u)};
#pragma unroll
                for (int i = 0; i < 8; i++) { s[i] = 0.f; q[i] = 0.f; }
#pragma unroll
                for (int k = 0; k < 20; k++) {
                    const uint32_t w[4] = {v[k].x, v[k].y, v[k].z, v[k].w};
#pragma unroll
                    for (int i = 0; i < 4; i++) {
                        const float a = __uint_as_float(w[i] << 16) - p0[2 * i], b = __uint_as_float(w[i] & 0xffff0000u) - p0[2 * i + 1];
                        s[2 * i] += a; s[2 * i + 1] += b; q[2 * i] = fmaf(a, a, q[2 * i]); q[2 * i + 1] = fmaf(b, b, q[2 * i + 1]);
                    }
                }
#pragma unroll
                for (int i = 0; i < 4; i++) {
                    const bool up = kg & 2;
                    const float ss = __shfl_xor_sync(~0u, up ? s[i] : s[i + 4], 16), qq = __shfl_xor_sync(~0u, up ? q[i] : q[i + 4], 16);
                    s[i] = (up ? s[i + 4] : s[i]) + ss; q[i] = (up ? q[i + 4] : q[i]) + qq; p0[i] = up ? p0[i + 4] : p0[i];
                }
#pragma unroll
                for (int i = 0; i < 2; i++) {
                    const bool up = kg & 1;
                    const float ss = __shfl_xor_sync(~0u, up ? s[i] : s[i + 2], 8), qq = __shfl_xor_sync(~0u, up ? q[i] : q[i + 2], 8);
                    s[i] = (up ? s[i + 2] : s[i]) + ss; q[i] = (up ? q[i + 2] : q[i]) + qq; p0[i] = up ? p0[i + 2] : p0[i];
                }
#pragma unroll
                for (int r = 0; r < 2; r++) {
                    const float d = s[r] * (1.0f / 80.0f);
                    st_tag2(g_part + (mb * 8 + hg) * 128 + 64 * r + j, __float_as_uint(p0[r] + d), __float_as_uint(fmaxf(fmaf(-d, s[r], q[r]), 0.f)), tag);
                }
                const ulonglong2* gp = g_part + mb * 8 * 128 + j;
#pragma unroll 1
                for (int it = 0; it < SPIN_MAX; it++) {
                    if (__all_sync(~0u, tag_ok(ld_tag2(gp + (j & 7) * 128 + 64), tag))) break;
                    __nanosleep(200);
                }
                ulonglong2 pw[16];
#pragma unroll 1
                for (int it = 0; it < SPIN_MAX; it++) {
                    bool ok = true;
#pragma unroll
                    for (int k = 0; k < 16; k++) pw[k] = ld_tag2(gp + k * 64);
#pragma unroll
                    for (int k = 0; k < 16; k++) ok = ok && tag_ok(pw[k], tag);
                    if (ok) break;
                    __nanosleep(200);
                }
                float o[4];
#pragma unroll
                for (int r = 0; r < 2; r++) {
                    float mean = 0.f, m2 = 0.f;
#pragma unroll
                    for (int k = 0; k < 8; k++) mean += __uint_as_float((uint32_t)pw[2 * k + r].x);
                    mean *= 0.125f;
#pragma unroll
                    for (int k = 0; k < 8; k++) {
                        const float dm = __uint_as_float((uint32_t)pw[2 * k + r].x) - mean;
                        m2 += fmaf(80.0f * dm, dm, __uint_as_float((uint32_t)pw[2 * k + r].y));
                    }
                    o[2 * r] = rbf(mean);
                    o[2 * r + 1] = rcp_apx(rbf(sqrt_apx(rbf(rbf(m2 * (1.0f / DM)) + 1e-5f))));
                }
                const int row = (j >> 5) * 64 + (j & 7) * 8 + ((j >> 3) & 3) * 2;
                *reinterpret_cast<float4*>(rst + row) = make_float4(o[0], o[1], o[2], o[3]);
                if (hg == 0) *reinterpret_cast<uint32_t*>(g_piv + SEQ + mb * 128 + row) = __byte_perm(__float_as_uint(o[0]), __float_as_uint(o[2]), 0x7632);
            }
            TSTAMP1T(7, 320);
            __syncwarp();
            if ((tid & 31) == 0) mbar_arrive(bar_stat);
        }
    } else {
        float acc[120];
#pragma unroll
        for (int i = 0; i < 120; i++) acc[i] = 0.f;
        const int lane = tid & 31, warp = w & 7, g = lane >> 2, t = lane & 3;
        if (on) {
            pdl_sync();
            SPAN(1 + 4 * layer, 1);
            TSTAMP1(0);
            if (threadIdx.x == 0) { GSTAMP(g_tim1, 15); }
            TSTAMP3(0);
            if (layer == 0) a1_mainloop<0>(acc, sbase, bars, wg, tile); else a1_mainloop<1>(acc, sbase, bars, wg, tile);
            mbar_wait(bar_stat, 0);
            mbar_wait(bars + 8 * (A1_NST + 3), 1);
            wgmma_wait<0>();
        }
        const float2 sa_ = rst[16 * warp + g], sb_ = rst[16 * warp + g + 8];
        TSTAMP1(2);
        TSTAMP1T(13, 224);
        uint32_t f[30][2];
        auto norm = [&](int j0) {
            float2 cc[10];
#pragma unroll
            for (int j = 0; j < 10; j++) cc[j] = *reinterpret_cast<const float2*>(cs + 8 * (j0 + j) + 2 * t);
#pragma unroll
            for (int j = 0; j < 10; j++) {
                const float* a = acc + 4 * (j0 + j);
                f[j0 + j][0] = pack2(fmaf(-sa_.x, cc[j].x, a[0]) * sa_.y, fmaf(-sa_.x, cc[j].y, a[1]) * sa_.y);
                f[j0 + j][1] = pack2(fmaf(-sb_.x, cc[j].x, a[2]) * sb_.y, fmaf(-sb_.x, cc[j].y, a[3]) * sb_.y);
            }
        };
        norm(10); norm(20);
        if (warp == 7) {
            uint4* hout = g_halo + ((layer * 16 + mb) * 8 + hg) * 320 + lane;
#pragma unroll
            for (int j = 0; j < 20; j += 2)
                asm volatile("st.relaxed.gpu.global.v4.u32 [%0], {%1,%2,%3,%4};" ::"l"(hout + 16 * j), "r"(f[10 + j][0]), "r"(f[10 + j][1]), "r"(f[11 + j][0]), "r"(f[11 + j][1]) : "memory");
        }
        TSTAMP1T(12, 224);
        const uint32_t kvw = sbase + A1_SM_KV + 16 * warp * A1_KVP;
        const uint32_t mrow = kvw + (lane & 15) * A1_KVP + (lane >> 4) * 16;
#pragma unroll
        for (int j = 0; j < 20; j += 2) stsm_x4(mrow + 16 * A1_KVP + 16 * j, f[10 + j][0], f[10 + j][1], f[11 + j][0], f[11 + j][1]);
        __syncwarp();
        if (lane == 0 && on) mbar_arrive(bar_kv + 8 * (warp + 1));
        norm(0);
        TSTAMP1T(10, 64);
        float sc[4][4][4];
        uint32_t qs[4][2];
#pragma unroll
        for (int h = 0; h < 4; h++) {
            const int jb = 5 * (h >> 1) + 3 * (h & 1), js = 5 * (h >> 1) + 2;
            qs[h][0] = (t >> 1) == (h & 1) ? f[js][0] : 0u; qs[h][1] = (t >> 1) == (h & 1) ? f[js][1] : 0u;
#pragma unroll
            for (int nt = 2; nt < 4; nt++) {
#pragma unroll
                for (int e = 0; e < 4; e++) sc[h][nt][e] = 0.f;
                mma_bf16(sc[h][nt], f[jb][0], f[jb][1], f[jb + 1][0], f[jb + 1][1], f[10 + jb][nt - 2], f[11 + jb][nt - 2]);
                mma_bf16_k8(sc[h][nt], qs[h][0], qs[h][1], f[10 + js][nt - 2]);
            }
        }
        if (on) mbar_wait(bar_kv + 8 * warp, 0);
        TSTAMP1(8);
        uint32_t kp[10][2];
#pragma unroll
        for (int j = 0; j < 10; j += 2) ldsm_x4(&kp[j][0], mrow + 16 * j);
#pragma unroll
        for (int h = 0; h < 4; h++) {
            const int jb = 5 * (h >> 1) + 3 * (h & 1), js = 5 * (h >> 1) + 2;
#pragma unroll
            for (int nt = 0; nt < 2; nt++) {
#pragma unroll
                for (int e = 0; e < 4; e++) sc[h][nt][e] = 0.f;
                mma_bf16(sc[h][nt], f[jb][0], f[jb][1], f[jb + 1][0], f[jb + 1][1], kp[jb][nt], kp[jb + 1][nt]);
                mma_bf16_k8(sc[h][nt], qs[h][0], qs[h][1], kp[js][nt]);
            }
        }
        uint32_t vb[10][4];
#pragma unroll
        for (int j = 0; j < 10; j++) ldsm_x4_t(vb[j], kvw + lane * A1_KVP + 160 + 16 * j);
        TSTAMP1T(3, 64);
        const bool odd = g & 1, hi = t > (g >> 1), edge = (mb | warp) == 0;
        float p[4][4], mx[4][2], sum[4][2];
#pragma unroll
        for (int h = 0; h < 4; h++) {
#pragma unroll
            for (int r = 0; r < 2; r++) {
                const float a = odd ? sc[h][1 + r][2 * r + 1] : sc[h][1 + r][2 * r];
                const float b0 = odd ? sc[h][r][2 * r + 1] : sc[h][r][2 * r], b1 = odd ? sc[h][2 + r][2 * r + 1] : sc[h][2 + r][2 * r];
                const uint32_t w1 = pack2(a, hi ? b0 : b1);
                const uint32_t w2 = pack2(__uint_as_float(w1 << 16) * 0.22360679774997896f, __uint_as_float(w1 & 0xffff0000u) * 0.22360679774997896f);
                p[h][2 * r] = __uint_as_float(w2 << 16); p[h][2 * r + 1] = __uint_as_float(w2 & 0xffff0000u);
            }
            if (edge) {
                p[h][0] = -1.0e9f;
                if (hi) { p[h][1] = -1.0e9f; p[h][3] = -1.0e9f; }
            }
            mx[h][0] = fmaxf(p[h][0], p[h][1]); mx[h][1] = fmaxf(p[h][2], p[h][3]);
        }
#pragma unroll
        for (int o = 1; o <= 2; o <<= 1)
#pragma unroll
            for (int h = 0; h < 4; h++)
#pragma unroll
                for (int r = 0; r < 2; r++) mx[h][r] = fmaxf(mx[h][r], __shfl_xor_sync(~0u, mx[h][r], o));
#pragma unroll
        for (int h = 0; h < 4; h++)
#pragma unroll
            for (int r = 0; r < 2; r++) {
                p[h][2 * r] = __expf(p[h][2 * r] - mx[h][r]); p[h][2 * r + 1] = __expf(p[h][2 * r + 1] - mx[h][r]);
                sum[h][r] = p[h][2 * r] + p[h][2 * r + 1];
            }
#pragma unroll
        for (int o = 1; o <= 2; o <<= 1)
#pragma unroll
            for (int h = 0; h < 4; h++)
#pragma unroll
                for (int r = 0; r < 2; r++) sum[h][r] += __shfl_xor_sync(~0u, sum[h][r], o);
        TSTAMP1T(5, 64);
        const uint32_t selA = odd ? 0x1044u : 0x4410u, selB = odd ? 0x3244u : 0x4432u, selH = hi ? selB : 0x4444u, selL = hi ? 0x4444u : selB;
        const uint32_t orow = sbase + A1_SM_O + (16 * warp + (lane & 15)) * 160 + (lane >> 4) * 16;
        uint32_t ob[10][2];
#pragma unroll
        for (int P = 0; P < 2; P++) {
            float os[2][4];
#pragma unroll
            for (int e = 0; e < 2; e++) {
                const int h = 2 * P + e;
                const float i0 = rcp_apx(sum[h][0]), i1 = rcp_apx(sum[h][1]);
                const uint32_t w0 = pack2(p[h][0] * i0, p[h][1] * i0), w1 = pack2(p[h][2] * i1, p[h][3] * i1);
                const uint32_t a00 = __byte_perm(w0, 0, selH), a02 = __byte_perm(w0, 0, selA), a03 = __byte_perm(w1, 0, selH);
                const uint32_t a10 = __byte_perm(w0, 0, selL), a11 = __byte_perm(w1, 0, selA), a13 = __byte_perm(w1, 0, selL);
#pragma unroll
                for (int dt = 0; dt < 3; dt++) {
                    const int j = 5 * P + (dt < 2 ? 3 * e + dt : 2);
                    float o[4] = {0.f, 0.f, 0.f, 0.f};
                    mma_bf16(o, a00, 0u, a02, a03, vb[j][0], vb[j][1]);
                    mma_bf16(o, a10, a11, 0u, a13, vb[j][2], vb[j][3]);
                    if (dt < 2) { ob[j][0] = pack2(o[0], o[1]); ob[j][1] = pack2(o[2], o[3]); }
                    else { os[e][0] = o[0]; os[e][1] = o[1]; os[e][2] = o[2]; os[e][3] = o[3]; }
                }
            }
            ob[5 * P + 2][0] = t < 2 ? pack2(os[0][0], os[0][1]) : pack2(os[1][0], os[1][1]);
            ob[5 * P + 2][1] = t < 2 ? pack2(os[0][2], os[0][3]) : pack2(os[1][2], os[1][3]);
        }
#pragma unroll
        for (int j = 0; j < 10; j += 2) stsm_x4(orow + 16 * j, ob[j][0], ob[j][1], ob[j + 1][0], ob[j + 1][1]);
        fence_async_smem();
        __syncwarp();
        if (on) {
            if (lane == 0) tma_store_2d(&tmOst, hg * 80, mb * 128 + 16 * warp, sbase + A1_SM_O + 16 * warp * 160);
            TSTAMP1T(4, 64);
            TSTAMP1(1);
            GSTAMP(g_tim1, 14);
            SPAN(1 + 4 * layer, 3);
            return;
        }
    }
    mbar_wait(bars + 144, 0);
    mbar_wait(bars + 8 * (A1_NST + 3), 1);
    const uint4* hin = g_halo + ((layer * 16 + mb - 1) * 8 + hg) * 320 + tid - 256;
    uint32_t hv[3][4] = {};
    if (mb > 0) {
#pragma unroll 1
        for (int it = 0; it < SPIN_MAX; it++) {
            bool ok = true;
#pragma unroll
            for (int k = 0; k < 3; k++)
                if (k < 2 || w < 10)
                    asm volatile("ld.relaxed.gpu.global.v4.u32 {%0,%1,%2,%3}, [%4];" : "=r"(hv[k][0]), "=r"(hv[k][1]), "=r"(hv[k][2]), "=r"(hv[k][3]) : "l"(hin + 128 * k) : "memory");
#pragma unroll
            for (int k = 0; k < 3; k++) ok = ok && hv[k][0] != ~0u && hv[k][1] != ~0u && hv[k][2] != ~0u && hv[k][3] != ~0u;
            if (ok) break;
        }
    }
    __syncwarp();
    TSTAMP1T(11, 256);
    const uint32_t hd = sbase + A1_SM_KV + (tid & 15) * A1_KVP + ((tid >> 4) & 1) * 16 + (w - 8) * 32;
#pragma unroll
    for (int k = 0; k < 3; k++)
        if (k < 2 || w < 10) stsm_x4(hd + 128 * k, hv[k][0], hv[k][1], hv[k][2], hv[k][3]);
    __syncwarp();
    if ((tid & 31) == 0) mbar_arrive(bar_kv);
}

constexpr int A2_THREADS = 288;
constexpr int A2_NA = 6;
#define A2_WPRE 4
#define A2_WLEAD 2
#define A2_RPOS 7
constexpr int A2_SM_A = 10 * WO_STAGE;
constexpr int A2_SM_R = A2_SM_A + A2_NA * 16384;
constexpr int A2_SM_BAR = A2_SM_R + 20480;
constexpr int A2_SMEM = A2_SM_BAR + 256 + 1024;

__global__ void __launch_bounds__(A2_THREADS, 1) a2_kernel(const int layer, const __grid_constant__ CUtensorMap tmO, const __grid_constant__ CUtensorMap tmR,
                                                           const __grid_constant__ CUtensorMap tmX1) {
    extern __shared__ unsigned char smraw[];
    const uint32_t sbase = (smem_u32(smraw) + 1023) & ~1023u;
    const uint32_t bars = sbase + A2_SM_BAR, bar_e = bars + 80, bar_r = bars + 128;
    const int tid = threadIdx.x, w = __shfl_sync(~0u, tid >> 5, 0), wg = w >> 2;
    const int tile = sm_tile();
    if (tile >= 128) { sm_idle(2 * layer + 1); return; }
    const int mb = tile >> 3, cg = tile & 7;
    if (wg == 2) {
        const unsigned char* wsrc = reinterpret_cast<const unsigned char*>(g_wo) + cg * 10 * WO_STAGE;
        if (tid == 256) {
            prefetch_tmap(&tmO);
#pragma unroll
            for (int i = 0; i < 17; i++) mbar_init(bars + 8 * i, i >= 10 && i < 16 ? 2 : 1);
            asm volatile("fence.mbarrier_init.release.cluster;" ::: "memory");
#pragma unroll
            for (int kb = 0; kb < A2_WPRE; kb += 2) {
                mbar_expect_tx(bars + 8 * kb, 16384 + 2 * WO_STAGE);
                bulk_load(sbase + kb * WO_STAGE, wsrc + kb * WO_STAGE, 2 * WO_STAGE, bars + 8 * kb);
            }
        }
        __syncwarp();
        asm volatile("bar.arrive 0, 288;" ::: "memory");
        if (tid == 256) {
#pragma unroll
            for (int kb = 0; kb < 10; kb++) if ((kb & 1) || kb >= A2_WPRE) mbar_expect_tx(bars + 8 * kb, (kb & 1) ? 16384 : 16384 + 2 * WO_STAGE);
            mbar_expect_tx(bar_r, 20480);
            pdl_sync();
#pragma unroll 1
            for (int kb = 0; kb < 10; kb++) {
                if (kb >= A2_NA) mbar_wait(bar_e + 8 * (kb - A2_NA), 0);
                tma_load_2d(sbase + A2_SM_A + (kb < A2_NA ? kb : kb - A2_NA) * 16384, &tmO, kb * 64, mb * 128, bars + 8 * kb);
                const int kw = kb + A2_WLEAD;
                if (!(kw & 1) && kw >= A2_WPRE && kw < 10) bulk_load(sbase + kw * WO_STAGE, wsrc + kw * WO_STAGE, 2 * WO_STAGE, bars + 8 * kw);
                if (kb == A2_RPOS) {
                    if (layer == 0) tma_load_2d(sbase + A2_SM_R, &tmR, cg * 80, mb * 128, bar_r);
                    else { tma_load_2d(sbase + A2_SM_R, &tmR, mb * 128, cg * 80, bar_r); tma_load_2d(sbase + A2_SM_R + 10240, &tmR, mb * 128 + 64, cg * 80, bar_r); }
                }
            }
        }
    } else {
        if (tid == 224) { prefetch_tmap(&tmR); prefetch_tmap(&tmX1); sm_started(2 * layer + 1); }
        asm volatile("bar.sync 0, 288;" ::: "memory");
        SPAN(2 + 4 * layer, 0);
        pdl_sync();
        SPAN(2 + 4 * layer, 1);
        TSTAMP2(0);
        TSTAMP4(0);
        if (threadIdx.x == 0) { GSTAMP(g_tim2, 15); }
        const int lane = tid & 31, warp = w, g = lane >> 2, t = lane & 3;
        const int row = layer * SEQ + mb * 128 + 16 * warp + g;
        const unsigned short pv0 = __ldcg(reinterpret_cast<const unsigned short*>(g_piv) + row), pv1 = __ldcg(reinterpret_cast<const unsigned short*>(g_piv) + row + 8);
        float acc[40];
#pragma unroll
        for (int i = 0; i < 40; i++) acc[i] = 0.f;
        const uint64_t da0 = make_desc(sbase + A2_SM_A + wg * 8192, 16, 1024, 1), db0 = make_desc(sbase, 16, 1024, 1);
#pragma unroll 1
        for (int kb = 0; kb < 10; kb++) {
            if (kb == 0) TSTAMP4(11);
            mbar_wait(bars + 8 * kb, 0);
            TSTAMP4(1 + kb);
            wgmma_fence();
#pragma unroll
            for (int kk = 0; kk < 4; kk++) wgmma_n80<0, 0>(acc, da0 + (uint32_t)((kb < A2_NA ? kb : kb - A2_NA) * 1024 + kk * 2), db0 + (uint32_t)(kb * (WO_STAGE / 16) + kk * 2));
            wgmma_commit();
            wgmma_wait<1>();
            if (kb > 0 && kb <= A2_NA && (tid & 127) == 0) mbar_arrive(bar_e + 8 * (kb - 1));
        }
        const uint32_t trow = ((lane & 7) + 8 * (lane >> 4)) * 128 + (((2 * (warp & 3) + ((lane >> 3) & 1)) ^ (lane & 7)) << 4);
        uint32_t xr[10][2];
        mbar_wait(bar_r, 0);
        if (layer == 0) {
#pragma unroll
            for (int j = 0; j < 10; j += 2) ldsm_x4(&xr[j][0], sbase + A2_SM_R + (16 * warp + (lane & 15)) * 160 + (lane >> 4) * 16 + 16 * j);
        } else {
#pragma unroll
            for (int j = 0; j < 10; j += 2) ldsm_x4_t(&xr[j][0], sbase + A2_SM_R + wg * 10240 + trow + 1024 * j);
        }
        mbar_wait(bar_e + 8 * (4 + wg), 0);
        wgmma_wait<0>();
        TSTAMP2(1);
        const float p0 = __uint_as_float((uint32_t)pv0 << 16), p1 = __uint_as_float((uint32_t)pv1 << 16);
        float s[4] = {0.f, 0.f, 0.f, 0.f};
#pragma unroll
        for (int j = 0; j < 10; j++) {
#pragma unroll
            for (int hh = 0; hh < 2; hh++) {
                const uint32_t a = pack2(acc[4 * j + 2 * hh], acc[4 * j + 2 * hh + 1]);
                const __nv_bfloat162 r = __hadd2_rn(*reinterpret_cast<const __nv_bfloat162*>(&xr[j][hh]), *reinterpret_cast<const __nv_bfloat162*>(&a));
                const uint32_t w = *reinterpret_cast<const uint32_t*>(&r);
                xr[j][hh] = w;
                const float d0 = __uint_as_float(w << 16) - (hh ? p1 : p0), d1 = __uint_as_float(w & 0xffff0000u) - (hh ? p1 : p0);
                s[2 * hh] += d0 + d1;
                s[2 * hh + 1] = fmaf(d0, d0, fmaf(d1, d1, s[2 * hh + 1]));
            }
        }
        const uint32_t so = sbase + A2_SM_A + (4 + wg) * 16384;
#pragma unroll
        for (int j = 0; j < 10; j += 2) stsm_x4_t(so + trow + 1024 * j, xr[j][0], xr[j][1], xr[j + 1][0], xr[j + 1][1]);
        fence_async_smem();
        TSTAMP2(2);
#pragma unroll
        for (int o = 1; o <= 2; o <<= 1)
#pragma unroll
            for (int i = 0; i < 4; i++) s[i] += __shfl_xor_sync(~0u, s[i], o);
        if (t < 2) asm volatile("red.relaxed.gpu.global.add.v2.f32 [%0], {%1, %2};" ::"l"(g_sum + layer * SEQ + (g >> 1) * 512 + (mb * 16 + 2 * warp + t) * 2 + (g & 1)), "f"(t ? s[2] : s[0]), "f"(t ? s[3] : s[1]) : "memory");
        if (wg) asm volatile("bar.sync 2, 128;" ::: "memory"); else asm volatile("bar.sync 1, 128;" ::: "memory");
        TSTAMP2(3);
        if ((tid & 127) == 0) tma_store_2d(&tmX1, mb * 128 + 64 * wg, cg * 80, so);
        TSTAMP2(4);
        GSTAMP(g_tim2, 14);
        SPAN(2 + 4 * layer, 3);
    }
}

static int h_nsm;
static void* h_sym[6];
static CUtensorMap h_tmX0, h_tmX1, h_tmOst, h_tmO, h_tmR0, h_tmR1, h_tmX1st, h_tmOut;
typedef CUresult (*PFN_encodeTiled)(CUtensorMap*, CUtensorMapDataType, cuuint32_t, void*, const cuuint64_t*, const cuuint64_t*,
                                    const cuuint32_t*, const cuuint32_t*, CUtensorMapInterleave, CUtensorMapSwizzle,
                                    CUtensorMapL2promotion, CUtensorMapFloatOOBfill);
static void make_tmap(CUtensorMap* tm, const void* ptr, uint64_t cols, uint64_t rows, uint32_t bc, uint32_t br, CUtensorMapSwizzle sw, uint64_t pitch = 0) {
    static PFN_encodeTiled fn = nullptr;
    if (!fn) {
        void* p = nullptr; cudaDriverEntryPointQueryResult qr;
        cudaGetDriverEntryPoint("cuTensorMapEncodeTiled", &p, cudaEnableDefault, &qr);
        fn = (PFN_encodeTiled)p;
    }
    cuuint64_t dims[2] = {cols, rows}; cuuint64_t strides[1] = {(pitch ? pitch : cols) * 2};
    cuuint32_t box[2] = {bc, br}; cuuint32_t es[2] = {1, 1};
    fn(tm, CU_TENSOR_MAP_DATA_TYPE_BFLOAT16, 2, const_cast<void*>(ptr), dims, strides, box, es, CU_TENSOR_MAP_INTERLEAVE_NONE, sw,
       CU_TENSOR_MAP_L2_PROMOTION_L2_128B, CU_TENSOR_MAP_FLOAT_OOB_FILL_NONE);
}
template <typename... Args>
static void launch_pdl(void (*kern)(Args...), int grid, int block, int smem, Args... args) {
    cudaLaunchConfig_t cfg = {};
    cfg.gridDim = dim3(grid); cfg.blockDim = dim3(block); cfg.dynamicSmemBytes = smem; cfg.stream = cudaStreamPerThread;
    cudaLaunchAttribute at[1];
    at[0].id = cudaLaunchAttributeProgrammaticStreamSerialization; at[0].val.programmaticStreamSerializationAllowed = 1;
    cfg.attrs = at; cfg.numAttrs = 1;
    cudaLaunchKernelEx(&cfg, kern, args...);
}
static void launch_stage(int k, void* const* d_in, void* d_out) {
    const KgIn kg = {(const bf16*)d_in[4], (const bf16*)d_in[5], (const bf16*)d_in[6], (const bf16*)d_in[7], (const bf16*)d_in[8], (const bf16*)d_in[0], (const bf16*)d_in[1], (const bf16*)d_in[2],
                      (uint4*)h_sym[0], (uint4*)h_sym[1], (uint4*)h_sym[2], (uint4*)h_sym[3], (uint4*)h_sym[4], (float*)h_sym[5]};
    switch (k) {
        case 0: kgen_kernel<<<DM, KG_THREADS, 0, cudaStreamPerThread>>>(kg); break;
        case 1: launch_pdl(a1_kernel, h_nsm, A1_THREADS, A1_SMEM, 0, (const bf16*)d_in[0], h_tmX0, h_tmR1, h_tmOst); break;
        case 2: launch_pdl(a2_kernel, h_nsm, A2_THREADS, A2_SMEM, 0, h_tmO, h_tmR0, h_tmX1st); break;
        case 3: launch_pdl(conv_kernel, DM / CV_CPB, CV_THREADS, CV_SMEM, (const bf16*)d_in[9], 0, h_tmOut); break;
        case 5: launch_pdl(a1_kernel, h_nsm, A1_THREADS, A1_SMEM, 1, (const bf16*)d_in[0], h_tmX1, h_tmR1, h_tmOst); break;
        case 6: launch_pdl(a2_kernel, h_nsm, A2_THREADS, A2_SMEM, 1, h_tmO, h_tmR1, h_tmX1st); break;
        case 7: launch_pdl(conv_kernel, DM / CV_CPB, CV_THREADS, CV_SMEM, (const bf16*)d_in[9], 1, h_tmOut); break;
        default: break;
    }
}
static int n_stage_kernels() { return 9; }
static const char* stage_name(int k) { const char* n[] = {"kgen", "a1", "a2", "conv", "tr", "a1", "a2", "conv", "tr"}; return n[k]; }

extern "C" void kernel_launch(void* const* d_in, const int* in_sizes, int n_in, void* d_out, int out_size) {
    (void)in_sizes; (void)n_in; (void)out_size;
    static const void *p_in = nullptr, *p_out = nullptr;
    if (p_in != d_in[0] || p_out != d_out) {
        cudaFuncSetAttribute(conv_kernel, cudaFuncAttributeMaxDynamicSharedMemorySize, CV_SMEM);
        cudaFuncSetAttribute(kgen_kernel, cudaFuncAttributePreferredSharedMemoryCarveout, 100);
        cudaFuncSetAttribute(a1_kernel, cudaFuncAttributeMaxDynamicSharedMemorySize, A1_SMEM);
        cudaFuncSetAttribute(a2_kernel, cudaFuncAttributeMaxDynamicSharedMemorySize, A2_SMEM);
        int dev; cudaGetDevice(&dev); cudaDeviceGetAttribute(&h_nsm, cudaDevAttrMultiProcessorCount, dev);
        if (h_nsm != 132) h_nsm = 128;
        cudaGetSymbolAddress(&h_sym[0], g_tap); cudaGetSymbolAddress(&h_sym[1], g_wq); cudaGetSymbolAddress(&h_sym[2], g_wo);
        cudaGetSymbolAddress(&h_sym[3], g_halo); cudaGetSymbolAddress(&h_sym[4], g_sum); cudaGetSymbolAddress(&h_sym[5], g_csp);
        void *po, *px1, *px2;
        cudaGetSymbolAddress(&po, g_o); cudaGetSymbolAddress(&px1, g_x1T); cudaGetSymbolAddress(&px2, g_xcT);
        make_tmap(&h_tmO, po, 640, 2048, 64, 128, CU_TENSOR_MAP_SWIZZLE_128B);
        make_tmap(&h_tmOst, po, 640, 2048, 80, 16, CU_TENSOR_MAP_SWIZZLE_NONE);
        make_tmap(&h_tmX0, d_in[0], 640, 2048, 64, 128, CU_TENSOR_MAP_SWIZZLE_128B);
        make_tmap(&h_tmX1, px2, 2048, 640, 64, 64, CU_TENSOR_MAP_SWIZZLE_128B, XCP);
        make_tmap(&h_tmR0, d_in[0], 640, 2048, 80, 128, CU_TENSOR_MAP_SWIZZLE_NONE);
        make_tmap(&h_tmR1, px2, 2048, 640, 64, 80, CU_TENSOR_MAP_SWIZZLE_128B, XCP);
        make_tmap(&h_tmX1st, px1, 2048, 640, 64, 80, CU_TENSOR_MAP_SWIZZLE_128B, XCP);
        make_tmap(&h_tmOut, d_out, 640, 2048, 80, 8, CU_TENSOR_MAP_SWIZZLE_NONE);
        p_in = d_in[0]; p_out = d_out;
    }
    for (int k = 0; k < n_stage_kernels(); k++) launch_stage(k, d_in, d_out);
}
```

```cpp
#include <cuda_runtime.h>
#include <cuda_bf16.h>
#include <stdint.h>
#include <cuda.h>

typedef __nv_bfloat16 bf16;

constexpr int SEQ = 2048;
constexpr int DM = 640;
constexpr int NMODE = 192;

__device__ __forceinline__ float bf2f(bf16 v) { return __bfloat162float(v); }
__device__ __forceinline__ float rbf(float v) {
    uint32_t r;
    asm("cvt.rn.bf16x2.f32 %0, %1, %2;" : "=r"(r) : "f"(v), "f"(0.f));
    return __uint_as_float(r);
}
__device__ __forceinline__ uint32_t pack2(float lo, float hi) {
    __nv_bfloat162 t = __floats2bfloat162_rn(lo, hi);
    return *reinterpret_cast<uint32_t*>(&t);
}
__device__ __forceinline__ void pdl_sync() {
    asm volatile("griddepcontrol.wait;" ::: "memory");
    asm volatile("griddepcontrol.launch_dependents;" ::: "memory");
}
__device__ __forceinline__ float sqrt_apx(float v) { float r; asm("sqrt.approx.ftz.f32 %0, %1;" : "=f"(r) : "f"(v)); return r; }
__device__ __forceinline__ float rcp_apx(float v) { float r; asm("rcp.approx.ftz.f32 %0, %1;" : "=f"(r) : "f"(v)); return r; }
__device__ __forceinline__ uint32_t smem_u32(const void* p) { return (uint32_t)__cvta_generic_to_shared(p); }

constexpr int TPAD = 16;
constexpr int DLEN = 544;
constexpr int TAP_W2 = DLEN * 8, TAP_W3 = TAP_W2 + 768, TAP_C = TAP_W3 + 768, TAPB = TAP_C + 384;
__device__ __align__(128) uint4 g_tap[DM * 128];
#define XPAD 64
constexpr int XCP = SEQ + XPAD;
__device__ __align__(128) bf16 g_x1T[DM * XCP];
__device__ __align__(128) bf16 g_xcT[DM * XCP];
__device__ __align__(128) bf16 g_o[SEQ * DM];
constexpr int WQ_STAGE = 240 * 128, WO_STAGE = 80 * 128;
__device__ __align__(128) uint4 g_wq[8 * 10 * WQ_STAGE / 16];
__device__ __align__(128) uint4 g_wo[8 * 10 * WO_STAGE / 16];
__device__ __align__(16) float g_csp[10 * 1920];
__device__ __align__(16) float2 g_sum[2 * SEQ];
__device__ __align__(16) bf16 g_piv[2 * SEQ];
__device__ __align__(128) bf16 g_yT[DM * XCP];
__device__ uint32_t g_epoch;
__device__ __align__(16) unsigned long long g_rstat[SEQ];
__device__ ulonglong2 g_part[16 * 8 * 128];
__device__ uint4 g_halo[2 * 128 * 320];
__device__ __forceinline__ unsigned long long tagw(uint32_t payload, uint32_t tag) { return ((unsigned long long)tag << 32) | payload; }
__device__ __forceinline__ void st_tag2(ulonglong2* p, uint32_t a, uint32_t b, uint32_t tag) {
    asm volatile("st.global.cg.v2.u64 [%0], {%1, %2};" ::"l"(p), "l"(tagw(a, tag)), "l"(tagw(b, tag)) : "memory");
}
__device__ __forceinline__ ulonglong2 ld_tag2(const ulonglong2* p) {
    ulonglong2 v;
    asm volatile("ld.relaxed.gpu.global.v2.u64 {%0, %1}, [%2];" : "=l"(v.x), "=l"(v.y) : "l"(p) : "memory");
    return v;
}
__device__ __forceinline__ bool tag_ok(ulonglong2 v, uint32_t tag) { return (uint32_t)(v.x >> 32) == tag && (uint32_t)(v.y >> 32) == tag; }
__device__ __forceinline__ uint32_t ld_epoch() { uint32_t v; asm volatile("ld.relaxed.gpu.global.u32 %0, [%1];" : "=r"(v) : "l"(&g_epoch) : "memory"); return v + 1; }
constexpr int SPIN_MAX = 1 << 20;
__device__ uint32_t g_started[4];
__device__ __forceinline__ void sm_started(int slot) { asm volatile("red.relaxed.gpu.global.add.u32 [%0], 1;" ::"l"(g_started + slot) : "memory"); }
__device__ __noinline__ void sm_idle(int slot) {
    if (threadIdx.x) return;
    sm_started(slot);
    const uint32_t want = ld_epoch() * gridDim.x;
    pdl_sync();
#pragma unroll 1
    for (int it = 0; it < SPIN_MAX; it++) {
        uint32_t v;
        asm volatile("ld.relaxed.gpu.global.u32 %0, [%1];" : "=r"(v) : "l"(g_started + slot) : "memory");
        if ((int)(v - want) >= 0) break;
        __nanosleep(100);
    }
}
__device__ __forceinline__ int sm_tile() {
    uint32_t s;
    asm volatile("mov.u32 %0, %smid;" : "=r"(s));
    const uint32_t h = (s - 64) >> 1, q = (h * 37) >> 8;
    const int t0 = ((s >> 1) & 7) * 16 + (s >> 4) * 2 + (s & 1), t1 = (1 + h - 7 * q) * 16 + 8 + q * 2 + (s & 1), t2 = s - 124 < 8 ? s - 116 : 128;
    return gridDim.x == 128 ? (int)blockIdx.x : s < 64 ? t0 : s < 120 ? t1 : t2;
}
#define DBG_SYMS
#define TSTAMP(i)
#define TSTAMP1(i)
#define TSTAMP1T(i, t)
#define TSTAMP1X(i, t)
#define SPAN(k, i)
#define GSTAMP(arr, i)
#define TSTAMP2(i)
#define TSTAMP3(i)
#define TSTAMP4(i)
#define TSTAMPK(i, t)

__device__ __forceinline__ void mma_bf16(float* d, uint32_t a0, uint32_t a1, uint32_t a2, uint32_t a3, uint32_t b0, uint32_t b1) {
    asm volatile("mma.sync.aligned.m16n8k16.row.col.f32.bf16.bf16.f32 {%0,%1,%2,%3}, {%4,%5,%6,%7}, {%8,%9}, {%0,%1,%2,%3};"
                 : "+f"(d[0]), "+f"(d[1]), "+f"(d[2]), "+f"(d[3]) : "r"(a0), "r"(a1), "r"(a2), "r"(a3), "r"(b0), "r"(b1));
}
__device__ __forceinline__ void mma_bf16_k8(float* d, uint32_t a0, uint32_t a1, uint32_t b0) {
    asm volatile("mma.sync.aligned.m16n8k8.row.col.f32.bf16.bf16.f32 {%0,%1,%2,%3}, {%4,%5}, {%6}, {%0,%1,%2,%3};"
                 : "+f"(d[0]), "+f"(d[1]), "+f"(d[2]), "+f"(d[3]) : "r"(a0), "r"(a1), "r"(b0));
}
__device__ __forceinline__ void ldsm_x4(uint32_t* r, uint32_t addr) {
    asm volatile("ldmatrix.sync.aligned.m8n8.x4.shared.b16 {%0,%1,%2,%3}, [%4];"
                 : "=r"(r[0]), "=r"(r[1]), "=r"(r[2]), "=r"(r[3]) : "r"(addr));
}

__device__ __forceinline__ void ldsm_x4_t(uint32_t* r, uint32_t addr) {
    asm volatile("ldmatrix.sync.aligned.m8n8.x4.trans.shared.b16 {%0,%1,%2,%3}, [%4];"
                 : "=r"(r[0]), "=r"(r[1]), "=r"(r[2]), "=r"(r[3]) : "r"(addr));
}
__device__ __forceinline__ void mbar_init(uint32_t bar, int count) { asm volatile("mbarrier.init.shared::cta.b64 [%0], %1;" ::"r"(bar), "r"(count)); }
__device__ __forceinline__ void mbar_arrive(uint32_t bar) { asm volatile("mbarrier.arrive.shared::cta.b64 _, [%0];" ::"r"(bar) : "memory"); }
__device__ __forceinline__ void mbar_wait(uint32_t bar, uint32_t parity) {
    asm volatile("{\n.reg .pred p;\nWAIT_LOOP:\n"
                 "mbarrier.try_wait.parity.shared::cta.b64 p, [%0], %1;\n"
                 "@p bra.uni WAIT_DONE;\nbra.uni WAIT_LOOP;\nWAIT_DONE:\n}" ::"r"(bar), "r"(parity) : "memory");
}

__device__ __forceinline__ void mbar_expect_tx(uint32_t bar, uint32_t bytes) {
    asm volatile("mbarrier.arrive.expect_tx.shared::cta.b64 _, [%0], %1;" ::"r"(bar), "r"(bytes) : "memory");
}
__device__ __forceinline__ void tma_load_2d(uint32_t dst, const void* tmap, int c0, int c1, uint32_t bar) {
    asm volatile("cp.async.bulk.tensor.2d.shared::cluster.global.mbarrier::complete_tx::bytes [%0], [%1, {%3, %4}], [%2];"
                 ::"r"(dst), "l"(tmap), "r"(bar), "r"(c0), "r"(c1) : "memory");
}
__device__ __forceinline__ void fence_async_smem() { asm volatile("fence.proxy.async.shared::cta;" ::: "memory"); }
__device__ __forceinline__ void bulk_load(uint32_t dst, const void* src, uint32_t bytes, uint32_t bar) {
    asm volatile("cp.async.bulk.shared::cluster.global.mbarrier::complete_tx::bytes [%0], [%1], %2, [%3];"
                 ::"r"(dst), "l"(src), "r"(bytes), "r"(bar) : "memory");
}
__device__ __forceinline__ void tma_store_2d(const void* tmap, int c0, int c1, uint32_t src) {
    asm volatile("cp.async.bulk.tensor.2d.global.shared::cta.bulk_group [%0, {%1, %2}], [%3];" ::"l"(tmap), "r"(c0), "r"(c1), "r"(src) : "memory");
    asm volatile("cp.async.bulk.commit_group;" ::: "memory");
    asm volatile("cp.async.bulk.wait_group.read 0;" ::: "memory");
}
__device__ __forceinline__ void stsm_x4(uint32_t addr, uint32_t r0, uint32_t r1, uint32_t r2, uint32_t r3) {
    asm volatile("stmatrix.sync.aligned.m8n8.x4.shared.b16 [%0], {%1,%2,%3,%4};" ::"r"(addr), "r"(r0), "r"(r1), "r"(r2), "r"(r3) : "memory");
}
__device__ __forceinline__ void stsm_x4_t(uint32_t addr, uint32_t r0, uint32_t r1, uint32_t r2, uint32_t r3) {
    asm volatile("stmatrix.sync.aligned.m8n8.x4.trans.shared.b16 [%0], {%1,%2,%3,%4};" ::"r"(addr), "r"(r0), "r"(r1), "r"(r2), "r"(r3) : "memory");
}
__device__ __forceinline__ void prefetch_tmap(const void* tmap) { asm volatile("prefetch.tensormap [%0];" ::"l"(tmap) : "memory"); }

__device__ __forceinline__ float2 cexp_at(float wr2, float wi, float p) {
    float er;
    asm("ex2.approx.ftz.f32 %0, %1;" : "=f"(er) : "f"(wr2 * p));
    float th = wi * p;
    const float k = rintf(th * 0.15915494309189535f);
    th = fmaf(k, -6.2831854820251465f, th);
    th = fmaf(k, 1.7484555314695172e-7f, th);
    return make_float2(er * __cosf(th), er * __sinf(th));
}
__device__ __forceinline__ float2 cmul(float2 a, float2 b) {
    return make_float2(fmaf(a.x, b.x, -a.y * b.y), fmaf(a.x, b.y, a.y * b.x));
}
__device__ __forceinline__ float2 csqr(float2 a) { return make_float2(fmaf(a.x, a.x, -a.y * a.y), (a.x + a.x) * a.y); }
__device__ __forceinline__ uint32_t packh(float2 v) {
    uint32_t r;
    asm("cvt.rn.f16x2.f32 %0, %1, %2;" : "=r"(r) : "f"(v.y), "f"(v.x));
    return r;
}
__device__ __forceinline__ void mma_f16(float* d, uint32_t a0, uint32_t a1, uint32_t a2, uint32_t a3, uint32_t b0, uint32_t b1) {
    asm volatile("mma.sync.aligned.m16n8k16.row.col.f32.f16.f16.f32 {%0,%1,%2,%3}, {%4,%5,%6,%7}, {%8,%9}, {%0,%1,%2,%3};"
                 : "+f"(d[0]), "+f"(d[1]), "+f"(d[2]), "+f"(d[3]) : "r"(a0), "r"(a1), "r"(a2), "r"(a3), "r"(b0), "r"(b1));
}

struct KgIn { const bf16 *logA, *Aim, *Cre, *Cim, *logdt, *x, *wqkv, *wo; uint4 *tap, *wq, *wop, *halo, *sum; float* csp; };
constexpr int KG_THREADS = NMODE / 2;

__global__ void __launch_bounds__(KG_THREADS, 5) kgen_kernel(const KgIn in, const __grid_constant__ CUtensorMap tmWq, const __grid_constant__ CUtensorMap tmWo) {
    __shared__ __align__(8) unsigned long long wbar[3];
    __shared__ __align__(1024) uint4 tab[3 * 896];
    const int d = blockIdx.x, tid = threadIdx.x, lane = tid & 31, warp = __shfl_sync(~0u, tid >> 5, 0);
    SPAN(0, 0); SPAN(0, 1);
    TSTAMPK(0, 0);
    asm volatile("griddepcontrol.launch_dependents;" ::: "memory");
    const bf16 pdt = in.logdt[d];
    const uint32_t pla = reinterpret_cast<const uint32_t*>(in.logA)[d * KG_THREADS + tid], pai = reinterpret_cast<const uint32_t*>(in.Aim)[d * KG_THREADS + tid];
    const uint32_t pcr = reinterpret_cast<const uint32_t*>(in.Cre)[d * KG_THREADS + tid], pci = reinterpret_cast<const uint32_t*>(in.Cim)[d * KG_THREADS + tid];
    const bf16* pfq = tid < 30 ? in.wqkv + (size_t)(d * 30 + tid) * 64 : tid < 40 ? in.wo + (size_t)(d * 10 + tid - 30) * 64 : in.x + (size_t)(d * 32 + tid - 40) * 64;
    if (tid < 72) asm volatile("prefetch.global.L2 [%0];" ::"l"(pfq));
    asm volatile("st.global.v4.u32 [%0], {%1,%1,%1,%1};" ::"l"(in.halo + d * 128 + tid), "r"(~0u));
    if (tid < 32) asm volatile("st.global.v4.u32 [%0], {%1,%1,%1,%1};" ::"l"(in.halo + d * 128 + 96 + tid), "r"(~0u));
    const uint32_t tw = smem_u32(tab) + warp * 14336;
    if (lane == 0) { mbar_init(smem_u32(wbar + warp), 1); prefetch_tmap(d >= 200 ? &tmWo : &tmWq); }
    const int g = lane >> 2, t = lane & 3;
    const uint32_t sta = tw + lane * 128 + ((2 * (lane & 3) + ((lane >> 2) & 1)) << 4);
    const uint32_t lda = tw + t * 128 + ((g ^ (2 * t)) << 4);
    const uint32_t stb = tw + 12288 + lane * 64 + ((4 * ((lane >> 1) & 1) + ((lane >> 2) & 3)) << 3);
    const uint32_t ldb = tw + 12288 + t * 64 + ((g ^ (4 * (t >> 1))) << 3);
    auto sts4 = [&](int e, int off, uint32_t a, uint32_t b, uint32_t c, uint32_t dd) {
        asm volatile("st.shared.v4.u32 [%0], {%1,%2,%3,%4};" ::"r"((sta ^ (e << 4)) + off), "r"(a), "r"(b), "r"(c), "r"(dd) : "memory");
    };
    auto lds4 = [&](int sp, int off, uint32_t* r) {
        asm volatile("ld.shared.v4.u32 {%0,%1,%2,%3}, [%4];" : "=r"(r[0]), "=r"(r[1]), "=r"(r[2]), "=r"(r[3]) : "r"((lda ^ ((sp & 1) << 4)) + sp * 512 + off) : "memory");
    };
    const float dt = rbf(expf(bf2f(pdt)));
    float2 C[2], y1[2], z8[2], y128[2];
    float cmax = 0.f;
#pragma unroll
    for (int m = 0; m < 2; m++) {
        const float wr2 = -rbf(expf(__uint_as_float(m ? pla & 0xffff0000u : pla << 16))) * dt * 1.4426950408889634f;
        const float wi = __uint_as_float(m ? pai & 0xffff0000u : pai << 16) * dt;
        C[m] = make_float2(__uint_as_float(m ? pcr & 0xffff0000u : pcr << 16) * dt, -__uint_as_float(m ? pci & 0xffff0000u : pci << 16) * dt);
        cmax = fmaxf(cmax, fmaxf(fabsf(C[m].x), fabsf(C[m].y)));
        y1[m] = cexp_at(wr2, -wi, 1.f); z8[m] = cexp_at(wr2, wi, 8.f); y128[m] = cexp_at(wr2, -wi, 128.f);
    }
    const int ex = min(max((int)(__reduce_max_sync(~0u, __float_as_uint(cmax)) >> 23), 20), 240);
    const float scale = __uint_as_float((uint32_t)(127 + 10 + 127 - ex) << 23), unscale = 2.0f * __uint_as_float((uint32_t)(ex - 10) << 23);
    TSTAMPK(4, 0);
    float k2048 = 0.f;
    float acc[5][4];
#pragma unroll
    for (int j = 0; j < 5; j++)
#pragma unroll
        for (int k = 0; k < 4; k++) acc[j][k] = 0.f;
    uint32_t af[8][4];
    {
        float2 h0[2], h1[2], g0[2], g1[2], g2[2], g2b[2], g3[2], g4[2], y2[2], y4[2];
#pragma unroll
        for (int m = 0; m < 2; m++) {
            h0[m] = make_float2(1.f, 0.f); h1[m] = csqr(csqr(csqr(z8[m])));
            g0[m] = make_float2(C[m].x * scale, C[m].y * scale);
            g1[m] = cmul(g0[m], y128[m]);
            const float2 y256 = csqr(y128[m]), y512 = csqr(y256);
            g2b[m] = g2[m] = cmul(g0[m], y256); g3[m] = cmul(g0[m], y512); g4[m] = cmul(g3[m], y512);
            y2[m] = csqr(y1[m]); y4[m] = csqr(y2[m]);
            const float2 y1024 = csqr(y512);
            k2048 += fmaf(g4[m].x, y1024.x, -g4[m].y * y1024.y);
        }
#pragma unroll
        for (int e = 0; e < 8; e++) {
            sts4(e, 0, packh(h0[0]), packh(h1[0]), packh(h0[1]), packh(h1[1]));
            sts4(e, 4096, packh(g0[0]), packh(g0[1]), packh(g1[0]), packh(g1[1]));
#pragma unroll
            for (int m = 0; m < 2; m++)
                if (e < 7) { h0[m] = e ? cmul(h0[m], z8[m]) : z8[m]; h1[m] = cmul(h1[m], z8[m]); g0[m] = cmul(g0[m], y1[m]); g1[m] = cmul(g1[m], y1[m]); }
            if (e < 5) k2048 += __shfl_xor_sync(~0u, k2048, 1 << e);
        }
        __syncwarp();
#pragma unroll
        for (int e = 0; e < 8; e++) {
            uint32_t b[4];
            lds4(e, 0, af[e]); lds4(e, 4096, b);
            sts4(e, 8192, packh(g2[0]), packh(g2[1]), packh((e & 1) ? cmul(g3[0], y4[0]) : g3[0]), packh((e & 1) ? cmul(g3[1], y4[1]) : g3[1]));
            asm volatile("st.shared.v2.u32 [%0], {%1,%2};" ::"r"(stb ^ (e << 3)), "r"(packh(g4[0])), "r"(packh(g4[1])) : "memory");
#pragma unroll
            for (int m = 0; m < 2; m++)
                if (e < 7) {
                    g2[m] = e == 3 ? cmul(g2b[m], y128[m]) : cmul(g2[m], y2[m]);
                    if (e & 1) g3[m] = cmul(g3[m], y128[m]);
                    g4[m] = cmul(g4[m], y128[m]);
                }
            mma_f16(acc[0], af[e][0], af[e][1], af[e][2], af[e][3], b[0], b[1]);
            mma_f16(acc[1], af[e][0], af[e][1], af[e][2], af[e][3], b[2], b[3]);
        }
    }
    TSTAMPK(6, 0);
    const int job = d * 3 + warp;
    const bool isq = job < 600;
    const int j2 = isq ? job : job - 600, scol = (j2 / 10) * 32, skb = j2 - (j2 / 10) * 10;
    fence_async_smem();
    __syncwarp();
    if (job < 800) {
        if (lane == 0) {
            mbar_expect_tx(smem_u32(wbar + warp), 4096);
            asm volatile("cp.async.bulk.tensor.4d.shared::cluster.global.mbarrier::complete_tx::bytes [%0], [%1, {%3, %4, %5, %4}], [%2];"
                         ::"r"(tw + 4096), "l"(isq ? &tmWq : &tmWo), "r"(smem_u32(wbar + warp)), "r"(scol), "r"(0), "r"(skb * 8) : "memory");
        }
    } else if (job < 800 + 64) in.sum[(job - 800) * 32 + lane] = make_uint4(0, 0, 0, 0);
#pragma unroll
    for (int sp = 0; sp < 8; sp++) {
        uint32_t c[4], e0, e1;
        lds4(sp, 8192, c);
        asm volatile("ld.shared.v2.u32 {%0,%1}, [%2];" : "=r"(e0), "=r"(e1) : "r"((ldb ^ ((sp & 3) << 3)) + sp * 256) : "memory");
        mma_f16(acc[2], af[sp][0], af[sp][1], af[sp][2], af[sp][3], c[0], c[1]);
        mma_f16(acc[3], af[sp][0], af[sp][1], af[sp][2], af[sp][3], c[2], c[3]);
        mma_f16(acc[4], af[sp][0], af[sp][1], af[sp][2], af[sp][3], e0, e1);
    }
    {
        float* Pp = reinterpret_cast<float*>(tab + warp * 896);
#pragma unroll
        for (int h = 0; h < 2; h++) {
            const int b = g + 8 * h;
            *reinterpret_cast<float2*>(Pp + 8 * b + 2 * t) = make_float2(acc[0][2 * h] * unscale, acc[0][2 * h + 1] * unscale);
            *reinterpret_cast<float2*>(Pp + 128 + 8 * b + 2 * t) = make_float2(acc[1][2 * h] * unscale, acc[1][2 * h + 1] * unscale);
            *reinterpret_cast<float2*>(Pp + 256 + 4 * b + 2 * (t & 1) + 64 * (t >> 1)) = make_float2(acc[2][2 * h] * unscale, acc[2][2 * h + 1] * unscale);
            *reinterpret_cast<float2*>(Pp + 384 + 2 * b + 32 * t) = make_float2(acc[3][2 * h] * unscale, acc[3][2 * h + 1] * unscale);
            Pp[512 + b + 32 * t] = acc[4][2 * h] * unscale;
            Pp[512 + b + 32 * t + 16] = acc[4][2 * h + 1] * unscale;
        }
        if (lane == 0) Pp[640] = k2048 * unscale;
    }
    TSTAMPK(7, 0);
    __syncthreads();
    TSTAMPK(9, 0);
    const float* Kp = reinterpret_cast<const float*>(tab);
    auto ksum = [&](int i) -> float { return (Kp[i] + Kp[3584 + i]) + Kp[7168 + i]; };
    auto ksum4 = [&](int q) -> float4 {
        const float4 a = reinterpret_cast<const float4*>(Kp)[q], b = reinterpret_cast<const float4*>(Kp)[896 + q], c = reinterpret_cast<const float4*>(Kp)[1792 + q];
        return make_float4((a.x + b.x) + c.x, (a.y + b.y) + c.y, (a.z + b.z) + c.z, (a.w + b.w) + c.w);
    };
    {
        uint2* E4 = reinterpret_cast<uint2*>(in.tap + d * 128);
        float4 v = ksum4(tid), u = ksum4(96 + min(tid, 64));
        const float cor = rbf(ksum(tid == 95 ? 384 : 512));
        if (tid == 95) v.w -= cor;
        if (tid == 31) u.w -= cor;
        const uint32_t lo = pack2(v.x, v.y), hi = pack2(v.z, v.w);
        if (tid < 64) {
            E4[6 + tid] = make_uint2(lo, hi);
            E4[(tid < 32 ? 159 : 209 - 32) + tid] = make_uint2(pack2(u.x, u.y), pack2(u.z, u.w));
        } else {
            const uint32_t nx = __shfl_down_sync(~0u, lo, 1);
            in.tap[d * 128 + 35 + tid - 64] = make_uint4(__byte_perm(lo, 0, 0x1010), __byte_perm(lo, hi, 0x5432), __byte_perm(hi, 0, 0x1010), __byte_perm(hi, tid == 95 ? 0u : nx, 0x5432));
            if (tid == 64) E4[241] = make_uint2(pack2(u.x, 0.f), 0u);
        }
    }
    TSTAMPK(10, 0);
    if (job < 800) {
        mbar_wait(smem_u32(wbar + warp), 0);
        const uint32_t src = tw + 4096 + ((lane >> 3) * 16 + (lane & 7)) * 64;
#pragma unroll
        for (int cg = 0; cg < 4; cg++) {
            const int col = scol + 8 * cg, sec = col / DM, r = col - sec * DM, hg = r / 80;
            const int n = isq ? hg * 160 + sec * 80 + r : col;
            unsigned char* dst = (isq ? reinterpret_cast<unsigned char*>(in.wq) + (hg * 9 + skb) * WQ_STAGE : reinterpret_cast<unsigned char*>(in.wop) + (hg * 9 + skb) * WO_STAGE) + (n + g) * 128;
            float cs[4] = {0.f, 0.f, 0.f, 0.f};
#pragma unroll
            for (int h = 0; h < 2; h++) {
                uint32_t w[4];
                ldsm_x4_t(w, src + h * 512 + ((cg ^ ((lane >> 1) & 3)) << 4));
                *reinterpret_cast<uint4*>(dst + (((4 * h + t) ^ g) << 4)) = make_uint4(w[0], w[1], w[2], w[3]);
                if (isq) {
                    mma_bf16(cs, 0x3f803f80u, 0u, 0x3f803f80u, 0u, w[0], w[1]);
                    mma_bf16(cs, 0x3f803f80u, 0u, 0x3f803f80u, 0u, w[2], w[3]);
                }
            }
            if (isq && g == cg) *reinterpret_cast<float2*>(in.csp + skb * 1920 + n + 2 * t) = make_float2(cs[0], cs[1]);
        }
    }
    TSTAMPK(11, 0);
    SPAN(0, 3);
}

#define CV_MODE 0
#define CV_SLEEP 100
constexpr int CV_CPB = 5;
constexpr int CV_THREADS = 512;
constexpr int UPADF = 128;
constexpr int ULEN = UPADF + SEQ + 80;
constexpr int XLEN = SEQ + 16;
constexpr int BX_5 = 0, BX_3 = 3264, BX_9 = 6528, BX_7 = 8960, BX_LEN = 11392;
constexpr int CV_SM_T = 0;
constexpr int CV_SM_B = CV_CPB * TAPB;
constexpr int CV_SM_U = CV_SM_B + CV_CPB * BX_LEN;
constexpr int CV_SM_X = CV_SM_U + CV_CPB * ULEN * 2;
constexpr int CV_SM_Y = CV_SM_X + CV_CPB * XLEN * 2;
constexpr int CV_SM_P = CV_SM_Y + CV_CPB * XLEN * 2;
constexpr int CV_SM_CNT = CV_SM_P + 6 * 4096;
constexpr int CV_SM_O = (CV_SM_CNT + 128 + 127) & ~127;
constexpr int CV_SMEM = CV_SM_O + 20480;
static_assert(CV_SM_B % 128 == 0 && CV_SM_CNT % 16 == 0, "layout");

__device__ __forceinline__ uint32_t ln2(uint32_t x, uint32_t m, float ra, float rb) {
    const __nv_bfloat162 d = __hsub2(*reinterpret_cast<const __nv_bfloat162*>(&x), *reinterpret_cast<const __nv_bfloat162*>(&m));
    const uint32_t w = *reinterpret_cast<const uint32_t*>(&d);
    return pack2(__uint_as_float(w << 16) * ra, __uint_as_float(w & 0xffff0000u) * rb);
}
__device__ __forceinline__ void cp_async16(uint32_t dst, const void* src) {
    asm volatile("cp.async.cg.shared.global [%0], [%1], 16;" ::"r"(dst), "l"(src));
}
__device__ __forceinline__ void cp_async_wait_all() { asm volatile("cp.async.wait_all;" ::: "memory"); }

template <bool FULL>
__device__ __forceinline__ void direct_pass(float (&acc)[8][4], uint32_t ub, uint32_t o0, uint32_t o1, const uint2* __restrict__ Tp, bool first_half) {
    uint32_t sw[8][8];
#pragma unroll
    for (int j = 0; j < 8; j++) { ldsm_x4(&sw[j][0], ub + o0 + j * 256); ldsm_x4(&sw[j][4], ub + o1 + j * 256); }
#pragma unroll
    for (int M = 0; M < 4; M++) {
#pragma unroll
        for (int i = 0; i < 4; i++) {
            const uint2 hi = Tp[128 * M + 16 * i], lo = Tp[128 * M + 16 * i - 8];
#pragma unroll
            for (int j = FULL ? 0 : M; j < 8; j++) mma_bf16(acc[j], hi.x, hi.y, lo.x, lo.y, sw[(j - M) & 7][2 * i], sw[(j - M) & 7][2 * i + 1]);
        }
        if (FULL) {
            ldsm_x4(&sw[7 - M][0], ub + o0 - (M + 1) * 256);
            if (M < 3) ldsm_x4(&sw[7 - M][4], ub + o1 - (M + 1) * 256);
        }
    }
    if (first_half) {
        const uint2 hi = Tp[512], lo = Tp[504];
#pragma unroll
        for (int j = FULL ? 0 : 4; j < 8; j++) mma_bf16(acc[j], hi.x, hi.y, lo.x, lo.y, sw[(j - 4) & 7][0], sw[(j - 4) & 7][1]);
    }
}
__device__ __forceinline__ uint32_t fin2(uint32_t x, uint32_t y, uint32_t u, uint32_t dk) {
    typedef __nv_bfloat162 b2;
    const b2 r = __hadd2_rn(*reinterpret_cast<const b2*>(&x), __hadd2_rn(*reinterpret_cast<const b2*>(&y),
                            __hmul2_rn(*reinterpret_cast<const b2*>(&u), *reinterpret_cast<const b2*>(&dk))));
    return *reinterpret_cast<const uint32_t*>(&r);
}
__global__ void __launch_bounds__(CV_THREADS, 1) conv_kernel(const bf16* __restrict__ Dskip, int layer, const __grid_constant__ CUtensorMap tmOut) {
    extern __shared__ __align__(128) unsigned char sm[];
    SPAN(3 + 4 * layer, 0);
    bf16* Us = reinterpret_cast<bf16*>(sm + CV_SM_U);
    bf16* Xs = reinterpret_cast<bf16*>(sm + CV_SM_X);
    bf16* Ys = reinterpret_cast<bf16*>(sm + CV_SM_Y);
    const int tid = threadIdx.x, lane = tid & 31, warp = __shfl_sync(~0u, tid >> 5, 0);
    const int d0 = blockIdx.x * CV_CPB, tile = blockIdx.x; (void)tile;
    TSTAMP1X(9, 256);
    unsigned short dskr;
    asm volatile("ld.global.nc.u16 %0, [%1];" : "=h"(dskr) : "l"(Dskip + d0 + min(lane, CV_CPB - 1)));
    if (tid >= 256) {
        const int t2 = tid - 256;
        if (t2 == 0) {
            mbar_init(smem_u32(sm + CV_SM_CNT) + 104, 1);
            asm volatile("fence.mbarrier_init.release.cluster;" ::: "memory");
            mbar_expect_tx(smem_u32(sm + CV_SM_CNT) + 104, CV_CPB * 2048);
            bulk_load(smem_u32(sm + CV_SM_O), g_tap + d0 * 128, CV_CPB * 2048, smem_u32(sm + CV_SM_CNT) + 104);
        } else if (lane == 0) {
            mbar_init(smem_u32(sm + CV_SM_CNT) + 16 * (warp - 9), warp == 15 ? 16 : 1);
            if (warp < 15) mbar_init(smem_u32(sm + CV_SM_CNT) + 16 * (warp - 9) + 8, 1);
            else if (layer) prefetch_tmap(&tmOut);
        }
        if (t2 < 149) {
            const int k = t2;
            const int off = k < 18 ? BX_5 + 8 * k : k < 37 ? BX_3 + 8 * (k - 18) : k < 69 ? BX_9 + 8 * (k - 37) : k < 101 ? BX_7 + 8 * (k - 69)
                          : k < 133 ? 8 * (k - 101) : (UPADF + SEQ) * 2 + 8 * (k - 133);
#pragma unroll
            for (int c = 0; c < CV_CPB; c++) *reinterpret_cast<uint2*>(sm + (k < 101 ? CV_SM_B + c * BX_LEN : CV_SM_U + c * ULEN * 2) + off) = make_uint2(0, 0);
        }
        asm volatile("bar.sync 1, 256;" ::: "memory");
        TSTAMP1X(10, 256);
        mbar_wait(smem_u32(sm + CV_SM_CNT) + 104, 0);
        TSTAMP1X(11, 256);
#pragma unroll 1
        for (int r = t2; r < 392; r += 256) {
            const bool dd = r < 272, cc = r >= 368;
            const uint32_t* E2 = reinterpret_cast<const uint32_t*>(sm + CV_SM_O) + (dd ? r + 3 : r < 320 ? 301 + 2 * (r - 272) : cc ? 417 : 401 + 2 * (r - 320));
            const uint32_t* E3 = E2 + (dd ? 4 : cc ? 0 : 1);
            const uint32_t s0 = !cc ? 0x7610u : r == 382 ? 0x1044u : 0x4444u, s1 = !cc ? 0x7610u : r == 378 ? 0x1044u : 0x4444u;
            const uint32_t s2 = !cc ? 0x1032u : r == 381 ? 0x4410u : 0x4444u, s3 = !cc ? 0x1032u : r == 377 ? 0x4410u : 0x4444u;
            uint32_t w[CV_CPB][4];
#pragma unroll
            for (int c = 0; c < CV_CPB; c++) { w[c][0] = E2[512 * c]; w[c][1] = E2[512 * c + 1]; w[c][2] = E3[512 * c]; w[c][3] = E3[512 * c + 1]; }
#pragma unroll
            for (int c = 0; c < CV_CPB; c++) {
                const uint32_t a = __byte_perm(w[c][3], w[c][2], s1), b = __byte_perm(w[c][1], w[c][0], s2);
                *reinterpret_cast<uint4*>(sm + CV_SM_T + c * TAPB + r * 16) =
                    make_uint4(__byte_perm(w[c][1], w[c][0], s0), dd || cc ? a : b, dd || cc ? b : a, __byte_perm(w[c][3], w[c][2], s3));
            }
        }
        TSTAMP1X(12, 256);
        if (layer == 0) {
#pragma unroll
            for (int c = 0; c < CV_CPB; c++) reinterpret_cast<uint4*>(g_yT + (size_t)(d0 + c) * XCP)[t2] = make_uint4(~0u, ~0u, ~0u, ~0u);
        }
        pdl_sync();
        if (layer && blockIdx.x == 0 && t2 == 0) g_epoch = ld_epoch();
    } else {
        const uint4* ppv = reinterpret_cast<const uint4*>(g_piv + layer * SEQ) + tid;
        const float4* psv = reinterpret_cast<const float4*>(g_sum + layer * SEQ) + tid;
        const uint4* pxv = reinterpret_cast<const uint4*>(g_x1T + (size_t)d0 * XCP) + tid;
        asm volatile("" : "+l"(ppv), "+l"(psv), "+l"(pxv));
        pdl_sync();
        SPAN(3 + 4 * layer, 1);
        TSTAMP(0);
        if (threadIdx.x == 0) { GSTAMP(g_tim, 15); }
        float4 sv[4];
#pragma unroll
        for (int k = 0; k < 4; k++) sv[k] = __ldcg(psv + 256 * k);
        const uint4 pv = __ldcg(ppv);
        uint4 xv[CV_CPB];
#pragma unroll
        for (int c = 0; c < CV_CPB; c++) xv[c] = __ldcg(pxv + c * (XCP / 8));
        uint32_t mw[4];
        float rs[8];
#pragma unroll
        for (int k = 0; k < 4; k++) {
            const uint32_t pw = k == 0 ? pv.x : k == 1 ? pv.y : k == 2 ? pv.z : pv.w;
            const float d0_ = sv[k].x * (1.0f / DM), d1_ = sv[k].z * (1.0f / DM);
            mw[k] = pack2(__uint_as_float(pw << 16) + d0_, __uint_as_float(pw & 0xffff0000u) + d1_);
            const uint32_t vr = pack2(fmaxf(fmaf(-d0_, d0_, sv[k].y * (1.0f / DM)), 0.f), fmaxf(fmaf(-d1_, d1_, sv[k].w * (1.0f / DM)), 0.f));
            const uint32_t ve = pack2(__uint_as_float(vr << 16) + 1e-5f, __uint_as_float(vr & 0xffff0000u) + 1e-5f);
            const uint32_t sd = pack2(sqrt_apx(__uint_as_float(ve << 16)), sqrt_apx(__uint_as_float(ve & 0xffff0000u)));
            rs[2 * k] = rcp_apx(__uint_as_float(sd << 16)); rs[2 * k + 1] = rcp_apx(__uint_as_float(sd & 0xffff0000u));
        }
        if (rs[0] != 123.f) TSTAMP(13);
        const int ch = tid + UPADF / 8, pch = ch ^ ((ch >> 3) & 1);
#pragma unroll
        for (int c = 0; c < CV_CPB; c++) {
            *reinterpret_cast<uint4*>(Xs + c * XLEN + tid * 8) = xv[c];
            *reinterpret_cast<uint4*>(Us + c * ULEN + pch * 8) =
                make_uint4(ln2(xv[c].x, mw[0], rs[0], rs[1]), ln2(xv[c].y, mw[1], rs[2], rs[3]), ln2(xv[c].z, mw[2], rs[4], rs[5]), ln2(xv[c].w, mw[3], rs[6], rs[7]));
        }
    }
    __syncthreads();
    TSTAMP(1);
    const uint32_t rstart = warp < 8 ? (warp < 4 ? 0x02000000u : 0x06040000u) : (warp < 12 ? 0x0C0B0A08u : 0x1E1D150Fu);
    const uint32_t rcount = warp < 8 ? 0x02020000u : (warp < 12 ? 0x03010102u : 0x01010806u);
#pragma unroll 1
    for (int rd = (rstart >> (8 * (warp & 3))) & 0xff, re = rd + ((rcount >> (8 * (warp & 3))) & 0xff); rd < re; rd++) {
        const int i = 32 * rd + lane;
        if (i < CV_CPB * 193) {
            const int c = i / 193, chunk = i - c * 193 - 1, ch = chunk + UPADF / 8;
            const bf16* uc = Us + c * ULEN;
            const uint4 o = *reinterpret_cast<const uint4*>(uc + (ch ^ ((ch >> 3) & 1)) * 8);
            const uint2 lo = *reinterpret_cast<const uint2*>(uc + ((ch - 1) ^ (((ch - 1) >> 3) & 1)) * 8 + 4);
            const uint2 hi = *reinterpret_cast<const uint2*>(uc + ((ch + 1) ^ (((ch + 1) >> 3) & 1)) * 8);
            const uint32_t w[8] = {lo.x, lo.y, o.x, o.y, o.z, o.w, hi.x, hi.y};
            float v[16], b[8];
#pragma unroll
            for (int k = 0; k < 8; k++) { v[2 * k] = __uint_as_float(w[k] << 16); v[2 * k + 1] = __uint_as_float(w[k] & 0xffff0000u); }
            unsigned char* bx = sm + CV_SM_B + c * BX_LEN + chunk * 16;
#pragma unroll
            for (int k = 0; k < 8; k++) b[k] = v[k + 4] + (v[k + 3] + v[k + 5]);
            *reinterpret_cast<uint2*>(bx + BX_3 + 168) = make_uint2(pack2(b[0], b[1]), pack2(b[2], b[3]));
            *reinterpret_cast<uint2*>(bx + BX_3 + 176) = make_uint2(pack2(b[4], b[5]), pack2(b[6], b[7]));
#pragma unroll
            for (int k = 0; k < 8; k++) b[k] += v[k + 2] + v[k + 6];
            *reinterpret_cast<uint4*>(bx + BX_5 + 160) = make_uint4(pack2(b[0], b[1]), pack2(b[2], b[3]), pack2(b[4], b[5]), pack2(b[6], b[7]));
            if (chunk < 128) {
#pragma unroll
                for (int k = 0; k < 8; k++) b[k] += v[k + 1] + v[k + 7];
                *reinterpret_cast<uint4*>(bx + BX_7 + 272) = make_uint4(pack2(b[0], b[1]), pack2(b[2], b[3]), pack2(b[4], b[5]), pack2(b[6], b[7]));
#pragma unroll
                for (int k = 0; k < 8; k++) b[k] += v[k] + v[k + 8];
                *reinterpret_cast<uint4*>(bx + BX_9 + 272) = make_uint4(pack2(b[0], b[1]), pack2(b[2], b[3]), pack2(b[4], b[5]), pack2(b[6], b[7]));
            }
        }
    }
    __syncwarp();
    if (lane == 0) mbar_arrive(smem_u32(sm + CV_SM_CNT) + 96);
    TSTAMP(2);
    {
        const int g = lane >> 2, ti = lane & 3;
        const int e = g - 2 * ti;
        uint32_t lds_off[4];
        uint32_t off2, off3, offc;
        {
            const int mat = lane >> 3, r = lane & 7;
#pragma unroll
            for (int pr = 0; pr < 4; pr++) {
                const int iw = 2 * pr + (mat >> 1), half = mat & 1;
                const int chunk = (UPADF - 16 * iw + 16 * r + 8 * half) >> 3;
                lds_off[pr] = (uint32_t)((chunk ^ ((chunk >> 3) & 1)) * 16);
            }
            const int j2 = 13 + r + 8 * (mat >> 1), j3 = j2 + 2, i0 = 8 * (mat & 1);
            off2 = (j2 & 1) ? BX_3 + (4 * j2 + i0 + 84) * 2 : BX_5 + (4 * j2 + i0 + 80) * 2;
            off3 = ((j3 & 1) ? BX_7 : BX_9) + (8 * j3 + i0 + 136) * 2;
            const int cc = (UPADF + 16 * (r + (mat >> 1)) + i0) >> 3;
            offc = (uint32_t)((cc ^ ((cc >> 3) & 1)) * 16);
        }
        const uint32_t rtab = warp < 8 ? (warp < 4 ? 0x0B090200u : 0x0C0A0301u) : (warp < 12 ? 0x13111008u : 0x1412241Cu);
        const int rl = (rtab >> (8 * (warp & 3))) & 0xff, type = rl >> 3, c = rl & 7;
        const int H = (type == 1 || type == 2) ? 1 : 0, T0 = 8 * H;
        const uint2* Tc = reinterpret_cast<const uint2*>(sm + CV_SM_T + c * TAPB) + TPAD + e;
        const uint32_t ubase = smem_u32(Us + c * ULEN);
        const uint32_t bbase = smem_u32(sm + CV_SM_B + c * BX_LEN);
        float acc[8][4];
#pragma unroll
        for (int j = 0; j < 8; j++)
#pragma unroll
            for (int k = 0; k < 4; k++) acc[j][k] = 0.f;
#pragma unroll 1
        for (int pass = (type == 2 || type == 4) ? 1 : 0; pass < ((type == 1 || type == 3) ? 1 : 2); pass++) {
            const uint32_t o0 = pass ? lds_off[2] : lds_off[0], o1 = pass ? lds_off[3] : lds_off[1];
            if (H) direct_pass<true>(acc, ubase + T0 * 256, o0, o1, Tc + 64 * pass, pass == 0);
            else direct_pass<false>(acc, ubase, o0, o1, Tc + 64 * pass, pass == 0);
        }
        TSTAMP(6);
        mbar_wait(smem_u32(sm + CV_SM_CNT) + 96, 0);
        if (type != 1 && type != 4) {
            const uint32_t* w2 = reinterpret_cast<const uint32_t*>(sm + CV_SM_T + c * TAPB + TAP_W2) + (115 - 96) + 4 * g - 2 * ti;
            uint32_t f[10][2];
#pragma unroll
            for (int k = 0; k < 10; k++) { f[k][0] = w2[16 * k]; f[k][1] = w2[16 * k - 8]; }
            const uint32_t ab = bbase + off2 + (2 * T0 + 6) * 128;
            const int kmax = H ? 23 : 8;
            uint32_t a[3][4];
            ldsm_x4_t(a[0], ab);
            ldsm_x4_t(a[1], ab - 128);
#pragma unroll
            for (int kp = 0; kp < 24; kp++) {
                if (kp > kmax) break;
                if (kp < 22) ldsm_x4_t(a[(kp + 2) % 3], ab - min(kp + 2, kmax) * 128);
#pragma unroll
                for (int j = 0; j < 8; j++) {
                    const int ee = 2 * j - 14 + kp;
                    if (ee >= 0 && ee <= 9) mma_bf16(acc[j], a[kp % 3][0], a[kp % 3][1], a[kp % 3][2], a[kp % 3][3], f[ee][0], f[ee][1]);
                }
            }
        }
        TSTAMP(7);
        if (type != 2 && type != 4) {
            const uint32_t* w3 = reinterpret_cast<const uint32_t*>(sm + CV_SM_T + c * TAPB + TAP_W3) + (129 - 96) + 2 * (g - ti);
            uint32_t f[9][2];
#pragma unroll
            for (int k = 0; k < 9; k++) { f[k][0] = w3[16 * k]; f[k][1] = w3[16 * k - 8]; }
            const uint32_t ab = bbase + off3 + (T0 - 2) * 256;
            uint32_t a[3][4];
            ldsm_x4_t(a[0], ab);
            ldsm_x4_t(a[1], ab - H * 256);
#pragma unroll
            for (int kp = 0; kp < 9; kp++) {
                if (kp > T0) break;
                if (kp < 7) ldsm_x4_t(a[(kp + 2) % 3], ab - min(kp + 2, T0) * 256);
#pragma unroll
                for (int j = 0; j < 8; j++) {
                    const int dl = j - 7 + kp;
                    if (dl >= 0 && dl <= 8) mma_bf16(acc[j], a[kp % 3][0], a[kp % 3][1], a[kp % 3][2], a[kp % 3][3], f[dl][0], f[dl][1]);
                }
            }
            const uint2* Dc = reinterpret_cast<const uint2*>(sm + CV_SM_T + c * TAPB + TAP_C) + e;
            const uint2 h63 = Dc[16], h64 = Dc[32], l63 = Dc[8], l64 = Dc[24];
#pragma unroll
            for (int j = 0; j < 8; j++)
                if (j == 7 || H) {
                    uint32_t bq[4];
                    ldsm_x4(bq, ubase + offc + (T0 + j - 8) * 256);
                    mma_bf16(acc[j], h64.x, h64.y, l64.x, l64.y, bq[0], bq[1]);
                    mma_bf16(acc[j], h63.x, h63.y, l63.x, l63.y, bq[2], bq[3]);
                }
        }
        TSTAMP(8);
        const bool hi_half = (type == 2 || type == 4);
        if (type != 0) {
            const int pair = H ? c : 5;
            float4* give = reinterpret_cast<float4*>(sm + CV_SM_P + pair * 4096 + (hi_half ? 2048 : 0)) + lane;
            const float4* take = reinterpret_cast<const float4*>(sm + CV_SM_P + pair * 4096 + (hi_half ? 0 : 2048)) + lane;
            const uint32_t pb = smem_u32(sm + CV_SM_CNT) + pair * 16;
#pragma unroll
            for (int j = 0; j < 4; j++)
                give[32 * j] = hi_half ? make_float4(acc[j][0], acc[j][1], acc[j][2], acc[j][3]) : make_float4(acc[j + 4][0], acc[j + 4][1], acc[j + 4][2], acc[j + 4][3]);
            __syncwarp();
            if (lane == 0) mbar_arrive(pb + (hi_half ? 8 : 0));
            mbar_wait(pb + (hi_half ? 0 : 8), 0);
#pragma unroll
            for (int j = 0; j < 4; j++) {
                const float4 v = take[32 * j];
                acc[j][0] = (hi_half ? acc[j + 4][0] : acc[j][0]) + v.x; acc[j][1] = (hi_half ? acc[j + 4][1] : acc[j][1]) + v.y;
                acc[j][2] = (hi_half ? acc[j + 4][2] : acc[j][2]) + v.z; acc[j][3] = (hi_half ? acc[j + 4][3] : acc[j][3]) + v.w;
            }
        }
        const uint32_t dk = __shfl_sync(~0u, (uint32_t)dskr, c) * 0x10001u;
#pragma unroll 1
        for (int rnd = 0; rnd < (type == 0 ? 2 : 1); rnd++) {
            const int Q = 2 * H + (hi_half ? 1 : rnd);
            if (rnd) {
#pragma unroll
                for (int j = 0; j < 4; j++)
#pragma unroll
                    for (int k = 0; k < 4; k++) acc[j][k] = acc[j + 4][k];
            }
            const uint32_t ya = smem_u32(Ys + c * XLEN) + (128 * (4 * Q + (lane >> 4)) + 16 * (lane & 7) + 8 * ((lane >> 3) & 1)) * 2;
#pragma unroll
            for (int j = 0; j < 4; j += 2)
                asm volatile("stmatrix.sync.aligned.m8n8.x4.trans.shared.b16 [%0], {%1,%2,%3,%4};" ::"r"(ya + j * 256),
                             "r"(pack2(acc[j][0], acc[j][1])), "r"(pack2(acc[j][2], acc[j][3])),
                             "r"(pack2(acc[j + 1][0], acc[j + 1][1])), "r"(pack2(acc[j + 1][2], acc[j + 1][3])) : "memory");
            __syncwarp();
            uint4 yv[2], xv[2], uv[2];
#pragma unroll
            for (int k = 0; k < 2; k++) {
                const int t = 512 * Q + 256 * k + 8 * lane, cu = (t + UPADF) >> 3;
                yv[k] = *reinterpret_cast<const uint4*>(Ys + c * XLEN + t);
                xv[k] = *reinterpret_cast<const uint4*>(Xs + c * XLEN + t);
                uv[k] = *reinterpret_cast<const uint4*>(Us + c * ULEN + (cu ^ ((cu >> 3) & 1)) * 8);
            }
#pragma unroll
            for (int k = 0; k < 2; k++)
                asm volatile("st.relaxed.gpu.global.v4.u32 [%0], {%1,%2,%3,%4};" ::"l"((layer ? g_yT : g_xcT) + (size_t)(d0 + c) * XCP + 512 * Q + 256 * k + 8 * lane),
                             "r"(fin2(xv[k].x, yv[k].x, uv[k].x, dk)), "r"(fin2(xv[k].y, yv[k].y, uv[k].y, dk)), "r"(fin2(xv[k].z, yv[k].z, uv[k].z, dk)), "r"(fin2(xv[k].w, yv[k].w, uv[k].w, dk)) : "memory");
        }
        TSTAMP(4);
        if (layer == 1) {
            const int mb = blockIdx.x >> 3, cg = blockIdx.x & 7;
            const bf16* src = g_yT + (size_t)(cg * 80 + (tid >> 4)) * XCP + mb * 128 + (tid & 15) * 8;
            uint32_t v[3][4];
            __syncthreads();
            TSTAMP(5);
            uint32_t todo = warp < 8 ? 7 : 3;
#pragma unroll 1
            for (int it = 0; it < SPIN_MAX; it++) {
#pragma unroll
                for (int k = 0; k < 3; k++)
                    if (todo >> k & 1)
                        asm volatile("ld.relaxed.gpu.global.v4.u32 {%0,%1,%2,%3}, [%4];" : "=r"(v[k][0]), "=r"(v[k][1]), "=r"(v[k][2]), "=r"(v[k][3]) : "l"(src + k * (32 * XCP)) : "memory");
#pragma unroll
                for (int k = 0; k < 3; k++)
                    if ((todo >> k & 1) && v[k][0] != ~0u && v[k][1] != ~0u && v[k][2] != ~0u && v[k][3] != ~0u) {
                        *reinterpret_cast<uint4*>(sm + (32 * k + (tid >> 4)) * 272 + (tid & 15) * 16) = make_uint4(v[k][0], v[k][1], v[k][2], v[k][3]);
                        todo ^= 1u << k;
                    }
                if (!todo) break;
                __nanosleep(CV_SLEEP);
            }
            __syncthreads();
            uint32_t w[12];
#pragma unroll
            for (int k = 0; k < 3; k++) ldsm_x4(&w[4 * k], smem_u32(sm) + min(32 * k + lane, 79) * 272 + warp * 16);
            const uint32_t ot = smem_u32(sm + CV_SM_O) + warp * 1280, oa = ot + (lane & 7) * 160 + (lane >> 3) * 16;
            stsm_x4_t(oa, w[0], w[1], w[2], w[3]);
            stsm_x4_t(oa + 64, w[4], w[5], w[6], w[7]);
            asm volatile("stmatrix.sync.aligned.m8n8.x2.trans.shared.b16 [%0], {%1,%2};" ::"r"(oa + 128), "r"(w[8]), "r"(w[9]) : "memory");
            fence_async_smem();
            __syncwarp();
            if (lane == 0) tma_store_2d(&tmOut, cg * 80, mb * 128 + 8 * warp, ot);
        }
    }
    TSTAMP(3);
    GSTAMP(g_tim, 14);
    SPAN(3 + 4 * layer, 3);
}

__device__ __forceinline__ void wgmma_fence() { asm volatile("wgmma.fence.sync.aligned;" ::: "memory"); }
__device__ __forceinline__ void wgmma_commit() { asm volatile("wgmma.commit_group.sync.aligned;" ::: "memory"); }
template <int N> __device__ __forceinline__ void wgmma_wait() { asm volatile("wgmma.wait_group.sync.aligned %0;" ::"n"(N) : "memory"); }
__device__ __forceinline__ uint64_t make_desc(uint32_t addr, uint32_t lbo, uint32_t sbo, uint32_t mode) {
    return (uint64_t)((addr & 0x3FFFF) >> 4) | ((uint64_t)(lbo >> 4) << 16) | ((uint64_t)(sbo >> 4) << 32) | ((uint64_t)mode << 62);
}
template <int TA, int TB>
__device__ __forceinline__ void wgmma_n240(float (&d)[120], uint64_t da, uint64_t db) {
    asm volatile("wgmma.mma_async.sync.aligned.m64n240k16.f32.bf16.bf16 {%0,%1,%2,%3,%4,%5,%6,%7,%8,%9,%10,%11,%12,%13,%14,%15,%16,%17,%18,%19,%20,%21,%22,%23,%24,%25,%26,%27,%28,%29,%30,%31,%32,%33,%34,%35,%36,%37,%38,%39,%40,%41,%42,%43,%44,%45,%46,%47,%48,%49,%50,%51,%52,%53,%54,%55,%56,%57,%58,%59,%60,%61,%62,%63,%64,%65,%66,%67,%68,%69,%70,%71,%72,%73,%74,%75,%76,%77,%78,%79,%80,%81,%82,%83,%84,%85,%86,%87,%88,%89,%90,%91,%92,%93,%94,%95,%96,%97,%98,%99,%100,%101,%102,%103,%104,%105,%106,%107,%108,%109,%110,%111,%112,%113,%114,%115,%116,%117,%118,%119}, %120, %121, 1, 1, 1, %122, %123;"
                 : "+f"(d[0]), "+f"(d[1]), "+f"(d[2]), "+f"(d[3]), "+f"(d[4]), "+f"(d[5]), "+f"(d[6]), "+f"(d[7]), "+f"(d[8]), "+f"(d[9]), "+f"(d[10]), "+f"(d[11]), "+f"(d[12]), "+f"(d[13]), "+f"(d[14]), "+f"(d[15]), "+f"(d[16]), "+f"(d[17]), "+f"(d[18]), "+f"(d[19]), "+f"(d[20]), "+f"(d[21]), "+f"(d[22]), "+f"(d[23]), "+f"(d[24]), "+f"(d[25]), "+f"(d[26]), "+f"(d[27]), "+f"(d[28]), "+f"(d[29]), "+f"(d[30]), "+f"(d[31]), "+f"(d[32]), "+f"(d[33]), "+f"(d[34]), "+f"(d[35]), "+f"(d[36]), "+f"(d[37]), "+f"(d[38]), "+f"(d[39]), "+f"(d[40]), "+f"(d[41]), "+f"(d[42]), "+f"(d[43]), "+f"(d[44]), "+f"(d[45]), "+f"(d[46]), "+f"(d[47]), "+f"(d[48]), "+f"(d[49]), "+f"(d[50]), "+f"(d[51]), "+f"(d[52]), "+f"(d[53]), "+f"(d[54]), "+f"(d[55]), "+f"(d[56]), "+f"(d[57]), "+f"(d[58]), "+f"(d[59]), "+f"(d[60]), "+f"(d[61]), "+f"(d[62]), "+f"(d[63]), "+f"(d[64]), "+f"(d[65]), "+f"(d[66]), "+f"(d[67]), "+f"(d[68]), "+f"(d[69]), "+f"(d[70]), "+f"(d[71]), "+f"(d[72]), "+f"(d[73]), "+f"(d[74]), "+f"(d[75]), "+f"(d[76]), "+f"(d[77]), "+f"(d[78]), "+f"(d[79]), "+f"(d[80]), "+f"(d[81]), "+f"(d[82]), "+f"(d[83]), "+f"(d[84]), "+f"(d[85]), "+f"(d[86]), "+f"(d[87]), "+f"(d[88]), "+f"(d[89]), "+f"(d[90]), "+f"(d[91]), "+f"(d[92]), "+f"(d[93]), "+f"(d[94]), "+f"(d[95]), "+f"(d[96]), "+f"(d[97]), "+f"(d[98]), "+f"(d[99]), "+f"(d[100]), "+f"(d[101]), "+f"(d[102]), "+f"(d[103]), "+f"(d[104]), "+f"(d[105]), "+f"(d[106]), "+f"(d[107]), "+f"(d[108]), "+f"(d[109]), "+f"(d[110]), "+f"(d[111]), "+f"(d[112]), "+f"(d[113]), "+f"(d[114]), "+f"(d[115]), "+f"(d[116]), "+f"(d[117]), "+f"(d[118]), "+f"(d[119])
                 : "l"(da), "l"(db), "n"(TA), "n"(TB));
}

template <int TA, int TB>
__device__ __forceinline__ void wgmma_n80(float (&d)[40], uint64_t da, uint64_t db) {
    asm volatile("wgmma.mma_async.sync.aligned.m64n80k16.f32.bf16.bf16 {%0,%1,%2,%3,%4,%5,%6,%7,%8,%9,%10,%11,%12,%13,%14,%15,%16,%17,%18,%19,%20,%21,%22,%23,%24,%25,%26,%27,%28,%29,%30,%31,%32,%33,%34,%35,%36,%37,%38,%39}, %40, %41, 1, 1, 1, %42, %43;"
                 : "+f"(d[0]), "+f"(d[1]), "+f"(d[2]), "+f"(d[3]), "+f"(d[4]), "+f"(d[5]), "+f"(d[6]), "+f"(d[7]), "+f"(d[8]), "+f"(d[9]), "+f"(d[10]), "+f"(d[11]), "+f"(d[12]), "+f"(d[13]), "+f"(d[14]), "+f"(d[15]), "+f"(d[16]), "+f"(d[17]), "+f"(d[18]), "+f"(d[19]), "+f"(d[20]), "+f"(d[21]), "+f"(d[22]), "+f"(d[23]), "+f"(d[24]), "+f"(d[25]), "+f"(d[26]), "+f"(d[27]), "+f"(d[28]), "+f"(d[29]), "+f"(d[30]), "+f"(d[31]), "+f"(d[32]), "+f"(d[33]), "+f"(d[34]), "+f"(d[35]), "+f"(d[36]), "+f"(d[37]), "+f"(d[38]), "+f"(d[39])
                 : "l"(da), "l"(db), "n"(TA), "n"(TB));
}

constexpr int A1_THREADS = 384;
constexpr int A1_NST = 4;
#define A1_PRE0 2
#define A1_SDELAY 1
#define A1_SKEW 8
#define A1_PRE1 1
constexpr int A1_STAGE = 16384 + WQ_STAGE;
constexpr int A1_KVP = 336;
constexpr int A1_SM_KV = 2 * A1_STAGE;
constexpr int A1_SM_O = A1_SM_KV + 144 * A1_KVP;
constexpr int A1_SM_R = A1_NST * A1_STAGE;
constexpr int A1_SM_BAR = A1_SM_R + 20480;
constexpr int A1_SM_CS = A1_SM_BAR + 256;
constexpr int A1_SM_RS = A1_SM_CS + 1024;
constexpr int A1_SMEM = A1_SM_RS + 1024 + 1024;
static_assert(A1_SM_O % 128 == 0 && A1_SM_O + 20480 <= A1_SM_R, "layout");

template <int L>
__device__ __forceinline__ void a1_mainloop(float (&acc)[120], uint32_t sbase, uint32_t bars, int wg, int tile) {
    constexpr int layer = L; (void)layer;
    const uint64_t da0 = L ? make_desc(sbase + wg * 8192, 8192, 1024, 1) : make_desc(sbase + wg * 8192, 16, 1024, 1), db0 = make_desc(sbase + 16384, 16, 1024, 1);
#pragma unroll 1
    for (int t = 0; t < 10; t++) {
        const int st = t % A1_NST;
        mbar_wait(bars + 8 * st, (t / A1_NST) & 1);
        if (t == A1_SKEW && wg == 0) mbar_wait(bars + 160, 0);
        TSTAMP3(1 + t);
        wgmma_fence();
#pragma unroll
        for (int kk = 0; kk < 4; kk++) wgmma_n240<L, 0>(acc, da0 + (uint32_t)(st * (A1_STAGE / 16) + kk * (L ? 128 : 2)), db0 + (uint32_t)(st * (A1_STAGE / 16) + kk * 2));
        wgmma_commit();
        if (t == 9 && threadIdx.x == 128) { mbar_arrive(bars + 160); mbar_arrive(bars + 144); }
        if (t == A1_SKEW - 1 && wg == 0) wgmma_wait<0>(); else wgmma_wait<1>();
        if (t > 0 && t < 9 && (threadIdx.x & 127) == 0) {
            if (t != A1_SKEW || wg) mbar_arrive(bars + 8 * (A1_NST + (t - 1) % A1_NST));
            if (t == A1_SKEW - 1 && wg == 0) mbar_arrive(bars + 8 * (A1_NST + t % A1_NST));
        }
    }
}

__global__ void __launch_bounds__(A1_THREADS, 1) a1_kernel(const int layer, const bf16* __restrict__ x0, const __grid_constant__ CUtensorMap tmX,
                                                           const __grid_constant__ CUtensorMap tmR, const __grid_constant__ CUtensorMap tmOst) {
    extern __shared__ unsigned char smraw[];
    const uint32_t sbase = (smem_u32(smraw) + 1023) & ~1023u;
    const uint32_t bars = sbase + A1_SM_BAR;
    const uint32_t bar_stat = bars + 64, bar_kv = bars + 72, bar_r = bars + 152;
    const int tid = threadIdx.x, w = __shfl_sync(~0u, tid >> 5, 0), wg = w >> 2;
    const int tile = sm_tile();
    if (tile >= 128) { sm_idle(2 * layer); return; }
    const int mb = (tile >> 2) & 15, hg = 4 * (tile >> 6) + (tile & 3);
    unsigned char* stg = smraw + (sbase - smem_u32(smraw));
    float* cs = reinterpret_cast<float*>(stg + A1_SM_CS);
    float2* rst = reinterpret_cast<float2*>(stg + A1_SM_RS);
    const int pre = layer ? A1_PRE1 : A1_PRE0;
    auto issue_w = [&](int kb) {
        bulk_load(sbase + (kb % A1_NST) * A1_STAGE + 16384, reinterpret_cast<const unsigned char*>(g_wq) + (hg * 10 + kb) * WQ_STAGE, WQ_STAGE, bars + 8 * (kb % A1_NST));
    };
    auto issue_x = [&](int kb) {
        const uint32_t dst = sbase + (kb % A1_NST) * A1_STAGE, full = bars + 8 * (kb % A1_NST);
        if (layer == 0) tma_load_2d(dst, &tmX, kb * 64, mb * 128, full);
        else { tma_load_2d(dst, &tmX, mb * 128, kb * 64, full); tma_load_2d(dst + 8192, &tmX, mb * 128 + 64, kb * 64, full); }
    };
    if (w == 8) {
        if (tid == 256) {
            prefetch_tmap(&tmX);
#pragma unroll
            for (int i = 0; i < A1_NST; i++) { mbar_init(bars + 8 * i, 1); mbar_init(bars + 8 * (A1_NST + i), 2); }
            mbar_init(bar_r, 1);
            asm volatile("fence.mbarrier_init.release.cluster;" ::: "memory");
#pragma unroll
            for (int i = 0; i < A1_NST; i++) mbar_expect_tx(bars + 8 * i, A1_STAGE);
            mbar_expect_tx(bar_r, 20480);
        }
        __syncwarp();
        asm volatile("bar.arrive 0, 384;" ::: "memory");
        if (tid == 256) {
#pragma unroll 1
            for (int kb = 0; kb < pre; kb++) { if (layer) issue_w(kb); else issue_x(kb); }
            pdl_sync();
#pragma unroll 1
            for (int kb = 0; kb < A1_NST; kb++) {
                if (kb == A1_SDELAY && layer) {
                    tma_load_2d(sbase + A1_SM_R, &tmR, mb * 128, hg * 80, bar_r); tma_load_2d(sbase + A1_SM_R + 10240, &tmR, mb * 128 + 64, hg * 80, bar_r);
                }
                if (kb >= pre || layer) issue_x(kb);
                if (kb >= pre || !layer) issue_w(kb);
            }
        }
    } else {
        if (tid == 0) {
            mbar_init(bar_stat, 2);
#pragma unroll
            for (int i = 0; i < 9; i++) mbar_init(bar_kv + 8 * i, i ? 1 : 4);
            mbar_init(bars + 144, 1);
            mbar_init(bars + 160, 1);
            asm volatile("fence.mbarrier_init.release.cluster;" ::: "memory");
        } else if (tid == 320) { prefetch_tmap(&tmR); prefetch_tmap(&tmOst); }
        asm volatile("bar.sync 0, 384;" ::: "memory");
    }
    SPAN(1 + 4 * layer, 0);
    const uint32_t tag = ld_epoch();
    if (tid == 352) sm_started(2 * layer);
    constexpr int on = 1;
    if (wg == 2) {
        if (w == 9) {
        } else if (w == 8) {
            if (tid == 256) {
#pragma unroll 1
                for (int kb = A1_NST; kb < 10; kb++) {
                    mbar_wait(bars + 8 * (A1_NST + kb % A1_NST), ((kb / A1_NST) - 1) & 1);
                    mbar_expect_tx(bars + 8 * (kb % A1_NST), A1_STAGE);
                    issue_x(kb); issue_w(kb);
                }
                TSTAMP1T(6, 256);
            }
            __syncwarp();
        } else {
            const int j = tid - 320;
            if (layer == 0) {
                const uint4* src = reinterpret_cast<const uint4*>(x0 + (size_t)(mb * 128 + hg * 16 + (j >> 2)) * DM);
                uint4 v[20];
#pragma unroll
                for (int k = 0; k < 20; k++) v[k] = __ldg(src + (j & 3) + 4 * k);
                const float p0 = __uint_as_float(__shfl_sync(~0u, v[0].x, j & 28) << 16);
                float s[2] = {0.f, 0.f}, q[2] = {0.f, 0.f};
#pragma unroll
                for (int k = 0; k < 20; k++) {
                    const uint32_t w[4] = {v[k].x, v[k].y, v[k].z, v[k].w};
#pragma unroll
                    for (int i = 0; i < 4; i++) {
                        const float a = __uint_as_float(w[i] << 16) - p0, b = __uint_as_float(w[i] & 0xffff0000u) - p0;
                        s[0] += a; s[1] += b; q[0] = fmaf(a, a, q[0]); q[1] = fmaf(b, b, q[1]);
                    }
                }
                float s0 = s[0] + s[1], q0 = q[0] + q[1];
#pragma unroll
                for (int o = 1; o <= 2; o <<= 1) { s0 += __shfl_xor_sync(~0u, s0, o); q0 += __shfl_xor_sync(~0u, q0, o); }
                if ((j & 3) == 0) {
                    const float d = s0 * (1.0f / DM);
                    const uint32_t ms = pack2(p0 + d, sqrt_apx(rbf(rbf(fmaxf(fmaf(-d, d, q0 * (1.0f / DM)), 0.f)) + 1e-5f)));
                    asm volatile("st.global.cg.u64 [%0], %1;" ::"l"(g_rstat + mb * 128 + hg * 16 + (j >> 2)), "l"(tagw(ms, tag)) : "memory");
                    g_piv[mb * 128 + hg * 16 + (j >> 2)] = __ushort_as_bfloat16((unsigned short)ms);
                }
                pdl_sync();
            }
            if (j < 60) {
                float4 a = make_float4(0.f, 0.f, 0.f, 0.f);
#pragma unroll
                for (int k = 0; k < 10; k++) {
                    const float4 v = __ldcg(reinterpret_cast<const float4*>(g_csp + k * 1920 + hg * 240) + j);
                    a.x += v.x; a.y += v.y; a.z += v.z; a.w += v.w;
                }
                reinterpret_cast<float4*>(cs)[j] = a;
            }
            if (layer == 0) {
                ulonglong2 v;
#pragma unroll 1
                for (int it = 0; it < SPIN_MAX; it++) {
                    v = ld_tag2(reinterpret_cast<const ulonglong2*>(g_rstat + mb * 128) + j);
                    if (tag_ok(v, tag)) break;
                    __nanosleep(100);
                }
                *reinterpret_cast<float4*>(rst + 2 * j) = make_float4(__uint_as_float((uint32_t)v.x << 16), rcp_apx(__uint_as_float((uint32_t)v.x & 0xffff0000u)),
                                                                      __uint_as_float((uint32_t)v.y << 16), rcp_apx(__uint_as_float((uint32_t)v.y & 0xffff0000u)));
            } else {
                const int ch = j & 7, kg = (j >> 3) & 3;
                const unsigned char* src = stg + A1_SM_R + (j >> 5) * 10240;
                mbar_wait(bar_r, 0);
                uint4 v[20];
#pragma unroll
                for (int k = 0; k < 20; k++) v[k] = *reinterpret_cast<const uint4*>(src + (4 * k + kg) * 128 + ((ch ^ ((4 * k + kg) & 7)) << 4));
                const uint4 pv = *reinterpret_cast<const uint4*>(src + (ch << 4));
                float s[8], q[8], p0[8] = {__uint_as_float(pv.x << 16), __uint_as_float(pv.x & 0xffff0000u), __uint_as_float(pv.y << 16), __uint_as_float(pv.y & 0xffff0000u),
                                           __uint_as_float(pv.z << 16), __uint_as_float(pv.z & 0xffff0000u), __uint_as_float(pv.w << 16), __uint_as_float(pv.w & 0xffff0000u)};
#pragma unroll
                for (int i = 0; i < 8; i++) { s[i] = 0.f; q[i] = 0.f; }
#pragma unroll
                for (int k = 0; k < 20; k++) {
                    const uint32_t w[4] = {v[k].x, v[k].y, v[k].z, v[k].w};
#pragma unroll
                    for (int i = 0; i < 4; i++) {
                        const float a = __uint_as_float(w[i] << 16) - p0[2 * i], b = __uint_as_float(w[i] & 0xffff0000u) - p0[2 * i + 1];
                        s[2 * i] += a; s[2 * i + 1] += b; q[2 * i] = fmaf(a, a, q[2 * i]); q[2 * i + 1] = fmaf(b, b, q[2 * i + 1]);
                    }
                }
#pragma unroll
                for (int i = 0; i < 4; i++) {
                    const bool up = kg & 2;
                    const float ss = __shfl_xor_sync(~0u, up ? s[i] : s[i + 4], 16), qq = __shfl_xor_sync(~0u, up ? q[i] : q[i + 4], 16);
                    s[i] = (up ? s[i + 4] : s[i]) + ss; q[i] = (up ? q[i + 4] : q[i]) + qq; p0[i] = up ? p0[i + 4] : p0[i];
                }
#pragma unroll
                for (int i = 0; i < 2; i++) {
                    const bool up = kg & 1;
                    const float ss = __shfl_xor_sync(~0u, up ? s[i] : s[i + 2], 8), qq = __shfl_xor_sync(~0u, up ? q[i] : q[i + 2], 8);
                    s[i] = (up ? s[i + 2] : s[i]) + ss; q[i] = (up ? q[i + 2] : q[i]) + qq; p0[i] = up ? p0[i + 2] : p0[i];
                }
#pragma unroll
                for (int r = 0; r < 2; r++) {
                    const float d = s[r] * (1.0f / 80.0f);
                    st_tag2(g_part + (mb * 8 + hg) * 128 + 64 * r + j, __float_as_uint(p0[r] + d), __float_as_uint(fmaxf(fmaf(-d, s[r], q[r]), 0.f)), tag);
                }
                const ulonglong2* gp = g_part + mb * 8 * 128 + j;
#pragma unroll 1
                for (int it = 0; it < SPIN_MAX; it++) {
                    if (__all_sync(~0u, tag_ok(ld_tag2(gp + (j & 7) * 128 + 64), tag))) break;
                    __nanosleep(200);
                }
                ulonglong2 pw[16];
#pragma unroll 1
                for (int it = 0; it < SPIN_MAX; it++) {
                    bool ok = true;
#pragma unroll
                    for (int k = 0; k < 16; k++) pw[k] = ld_tag2(gp + k * 64);
#pragma unroll
                    for (int k = 0; k < 16; k++) ok = ok && tag_ok(pw[k], tag);
                    if (ok) break;
                    __nanosleep(200);
                }
                float o[4];
#pragma unroll
                for (int r = 0; r < 2; r++) {
                    float mean = 0.f, m2 = 0.f;
#pragma unroll
                    for (int k = 0; k < 8; k++) mean += __uint_as_float((uint32_t)pw[2 * k + r].x);
                    mean *= 0.125f;
#pragma unroll
                    for (int k = 0; k < 8; k++) {
                        const float dm = __uint_as_float((uint32_t)pw[2 * k + r].x) - mean;
                        m2 += fmaf(80.0f * dm, dm, __uint_as_float((uint32_t)pw[2 * k + r].y));
                    }
                    o[2 * r] = rbf(mean);
                    o[2 * r + 1] = rcp_apx(rbf(sqrt_apx(rbf(rbf(m2 * (1.0f / DM)) + 1e-5f))));
                }
                const int row = (j >> 5) * 64 + (j & 7) * 8 + ((j >> 3) & 3) * 2;
                *reinterpret_cast<float4*>(rst + row) = make_float4(o[0], o[1], o[2], o[3]);
                if (hg == 0) *reinterpret_cast<uint32_t*>(g_piv + SEQ + mb * 128 + row) = __byte_perm(__float_as_uint(o[0]), __float_as_uint(o[2]), 0x7632);
            }
            TSTAMP1T(7, 320);
            __syncwarp();
            if ((tid & 31) == 0) mbar_arrive(bar_stat);
        }
    } else {
        float acc[120];
#pragma unroll
        for (int i = 0; i < 120; i++) acc[i] = 0.f;
        const int lane = tid & 31, warp = w & 7, g = lane >> 2, t = lane & 3;
        if (on) {
            pdl_sync();
            SPAN(1 + 4 * layer, 1);
            TSTAMP1(0);
            if (threadIdx.x == 0) { GSTAMP(g_tim1, 15); }
            TSTAMP3(0);
            if (layer == 0) a1_mainloop<0>(acc, sbase, bars, wg, tile); else a1_mainloop<1>(acc, sbase, bars, wg, tile);
            mbar_wait(bar_stat, 0);
            mbar_wait(bars + 8 * (A1_NST + 3), 1);
            wgmma_wait<0>();
        }
        const float2 sa_ = rst[16 * warp + g], sb_ = rst[16 * warp + g + 8];
        TSTAMP1(2);
        TSTAMP1T(13, 224);
        uint32_t f[30][2];
        auto norm = [&](int j0) {
            float2 cc[10];
#pragma unroll
            for (int j = 0; j < 10; j++) cc[j] = *reinterpret_cast<const float2*>(cs + 8 * (j0 + j) + 2 * t);
#pragma unroll
            for (int j = 0; j < 10; j++) {
                const float* a = acc + 4 * (j0 + j);
                f[j0 + j][0] = pack2(fmaf(-sa_.x, cc[j].x, a[0]) * sa_.y, fmaf(-sa_.x, cc[j].y, a[1]) * sa_.y);
                f[j0 + j][1] = pack2(fmaf(-sb_.x, cc[j].x, a[2]) * sb_.y, fmaf(-sb_.x, cc[j].y, a[3]) * sb_.y);
            }
        };
        norm(10); norm(20);
        if (warp == 7) {
            uint4* hout = g_halo + ((layer * 16 + mb) * 8 + hg) * 320 + lane;
#pragma unroll
            for (int j = 0; j < 20; j += 2)
                asm volatile("st.relaxed.gpu.global.v4.u32 [%0], {%1,%2,%3,%4};" ::"l"(hout + 16 * j), "r"(f[10 + j][0]), "r"(f[10 + j][1]), "r"(f[11 + j][0]), "r"(f[11 + j][1]) : "memory");
        }
        TSTAMP1T(12, 224);
        const uint32_t kvw = sbase + A1_SM_KV + 16 * warp * A1_KVP;
        const uint32_t mrow = kvw + (lane & 15) * A1_KVP + (lane >> 4) * 16;
#pragma unroll
        for (int j = 0; j < 20; j += 2) stsm_x4(mrow + 16 * A1_KVP + 16 * j, f[10 + j][0], f[10 + j][1], f[11 + j][0], f[11 + j][1]);
        __syncwarp();
        if (lane == 0 && on) mbar_arrive(bar_kv + 8 * (warp + 1));
        norm(0);
        TSTAMP1T(10, 64);
        float sc[4][4][4];
        uint32_t qs[4][2];
#pragma unroll
        for (int h = 0; h < 4; h++) {
            const int jb = 5 * (h >> 1) + 3 * (h & 1), js = 5 * (h >> 1) + 2;
            qs[h][0] = (t >> 1) == (h & 1) ? f[js][0] : 0u; qs[h][1] = (t >> 1) == (h & 1) ? f[js][1] : 0u;
#pragma unroll
            for (int nt = 2; nt < 4; nt++) {
#pragma unroll
                for (int e = 0; e < 4; e++) sc[h][nt][e] = 0.f;
                mma_bf16(sc[h][nt], f[jb][0], f[jb][1], f[jb + 1][0], f[jb + 1][1], f[10 + jb][nt - 2], f[11 + jb][nt - 2]);
                mma_bf16_k8(sc[h][nt], qs[h][0], qs[h][1], f[10 + js][nt - 2]);
            }
        }
        if (on) mbar_wait(bar_kv + 8 * warp, 0);
        TSTAMP1(8);
        uint32_t kp[10][2];
#pragma unroll
        for (int j = 0; j < 10; j += 2) ldsm_x4(&kp[j][0], mrow + 16 * j);
#pragma unroll
        for (int h = 0; h < 4; h++) {
            const int jb = 5 * (h >> 1) + 3 * (h & 1), js = 5 * (h >> 1) + 2;
#pragma unroll
            for (int nt = 0; nt < 2; nt++) {
#pragma unroll
                for (int e = 0; e < 4; e++) sc[h][nt][e] = 0.f;
                mma_bf16(sc[h][nt], f[jb][0], f[jb][1], f[jb + 1][0], f[jb + 1][1], kp[jb][nt], kp[jb + 1][nt]);
                mma_bf16_k8(sc[h][nt], qs[h][0], qs[h][1], kp[js][nt]);
            }
        }
        uint32_t vb[10][4];
#pragma unroll
        for (int j = 0; j < 10; j++) ldsm_x4_t(vb[j], kvw + lane * A1_KVP + 160 + 16 * j);
        TSTAMP1T(3, 64);
        const bool odd = g & 1, hi = t > (g >> 1), edge = (mb | warp) == 0;
        float p[4][4], mx[4][2], sum[4][2];
#pragma unroll
        for (int h = 0; h < 4; h++) {
#pragma unroll
            for (int r = 0; r < 2; r++) {
                const float a = odd ? sc[h][1 + r][2 * r + 1] : sc[h][1 + r][2 * r];
                const float b0 = odd ? sc[h][r][2 * r + 1] : sc[h][r][2 * r], b1 = odd ? sc[h][2 + r][2 * r + 1] : sc[h][2 + r][2 * r];
                const uint32_t w1 = pack2(a, hi ? b0 : b1);
                const uint32_t w2 = pack2(__uint_as_float(w1 << 16) * 0.22360679774997896f, __uint_as_float(w1 & 0xffff0000u) * 0.22360679774997896f);
                p[h][2 * r] = __uint_as_float(w2 << 16); p[h][2 * r + 1] = __uint_as_float(w2 & 0xffff0000u);
            }
            if (edge) {
                p[h][0] = -1.0e9f;
                if (hi) { p[h][1] = -1.0e9f; p[h][3] = -1.0e9f; }
            }
            mx[h][0] = fmaxf(p[h][0], p[h][1]); mx[h][1] = fmaxf(p[h][2], p[h][3]);
        }
#pragma unroll
        for (int o = 1; o <= 2; o <<= 1)
#pragma unroll
            for (int h = 0; h < 4; h++)
#pragma unroll
                for (int r = 0; r < 2; r++) mx[h][r] = fmaxf(mx[h][r], __shfl_xor_sync(~0u, mx[h][r], o));
#pragma unroll
        for (int h = 0; h < 4; h++)
#pragma unroll
            for (int r = 0; r < 2; r++) {
                p[h][2 * r] = __expf(p[h][2 * r] - mx[h][r]); p[h][2 * r + 1] = __expf(p[h][2 * r + 1] - mx[h][r]);
                sum[h][r] = p[h][2 * r] + p[h][2 * r + 1];
            }
#pragma unroll
        for (int o = 1; o <= 2; o <<= 1)
#pragma unroll
            for (int h = 0; h < 4; h++)
#pragma unroll
                for (int r = 0; r < 2; r++) sum[h][r] += __shfl_xor_sync(~0u, sum[h][r], o);
        TSTAMP1T(5, 64);
        const uint32_t selA = odd ? 0x1044u : 0x4410u, selB = odd ? 0x3244u : 0x4432u, selH = hi ? selB : 0x4444u, selL = hi ? 0x4444u : selB;
        const uint32_t orow = sbase + A1_SM_O + (16 * warp + (lane & 15)) * 160 + (lane >> 4) * 16;
        uint32_t ob[10][2];
#pragma unroll
        for (int P = 0; P < 2; P++) {
            float os[2][4];
#pragma unroll
            for (int e = 0; e < 2; e++) {
                const int h = 2 * P + e;
                const float i0 = rcp_apx(sum[h][0]), i1 = rcp_apx(sum[h][1]);
                const uint32_t w0 = pack2(p[h][0] * i0, p[h][1] * i0), w1 = pack2(p[h][2] * i1, p[h][3] * i1);
                const uint32_t a00 = __byte_perm(w0, 0, selH), a02 = __byte_perm(w0, 0, selA), a03 = __byte_perm(w1, 0, selH);
                const uint32_t a10 = __byte_perm(w0, 0, selL), a11 = __byte_perm(w1, 0, selA), a13 = __byte_perm(w1, 0, selL);
#pragma unroll
                for (int dt = 0; dt < 3; dt++) {
                    const int j = 5 * P + (dt < 2 ? 3 * e + dt : 2);
                    float o[4] = {0.f, 0.f, 0.f, 0.f};
                    mma_bf16(o, a00, 0u, a02, a03, vb[j][0], vb[j][1]);
                    mma_bf16(o, a10, a11, 0u, a13, vb[j][2], vb[j][3]);
                    if (dt < 2) { ob[j][0] = pack2(o[0], o[1]); ob[j][1] = pack2(o[2], o[3]); }
                    else { os[e][0] = o[0]; os[e][1] = o[1]; os[e][2] = o[2]; os[e][3] = o[3]; }
                }
            }
            ob[5 * P + 2][0] = t < 2 ? pack2(os[0][0], os[0][1]) : pack2(os[1][0], os[1][1]);
            ob[5 * P + 2][1] = t < 2 ? pack2(os[0][2], os[0][3]) : pack2(os[1][2], os[1][3]);
        }
#pragma unroll
        for (int j = 0; j < 10; j += 2) stsm_x4(orow + 16 * j, ob[j][0], ob[j][1], ob[j + 1][0], ob[j + 1][1]);
        fence_async_smem();
        __syncwarp();
        if (on) {
            if (lane == 0) tma_store_2d(&tmOst, hg * 80, mb * 128 + 16 * warp, sbase + A1_SM_O + 16 * warp * 160);
            TSTAMP1T(4, 64);
            TSTAMP1(1);
            GSTAMP(g_tim1, 14);
            SPAN(1 + 4 * layer, 3);
            return;
        }
    }
    mbar_wait(bars + 144, 0);
    mbar_wait(bars + 8 * (A1_NST + 3), 1);
    const uint4* hin = g_halo + ((layer * 16 + mb - 1) * 8 + hg) * 320 + tid - 256;
    uint32_t hv[3][4] = {};
    if (mb > 0) {
#pragma unroll 1
        for (int it = 0; it < SPIN_MAX; it++) {
            bool ok = true;
#pragma unroll
            for (int k = 0; k < 3; k++)
                if (k < 2 || w < 10)
                    asm volatile("ld.relaxed.gpu.global.v4.u32 {%0,%1,%2,%3}, [%4];" : "=r"(hv[k][0]), "=r"(hv[k][1]), "=r"(hv[k][2]), "=r"(hv[k][3]) : "l"(hin + 128 * k) : "memory");
#pragma unroll
            for (int k = 0; k < 3; k++) ok = ok && hv[k][0] != ~0u && hv[k][1] != ~0u && hv[k][2] != ~0u && hv[k][3] != ~0u;
            if (ok) break;
        }
    }
    __syncwarp();
    TSTAMP1T(11, 256);
    const uint32_t hd = sbase + A1_SM_KV + (tid & 15) * A1_KVP + ((tid >> 4) & 1) * 16 + (w - 8) * 32;
#pragma unroll
    for (int k = 0; k < 3; k++)
        if (k < 2 || w < 10) stsm_x4(hd + 128 * k, hv[k][0], hv[k][1], hv[k][2], hv[k][3]);
    __syncwarp();
    if ((tid & 31) == 0) mbar_arrive(bar_kv);
}

constexpr int A2_THREADS = 288;
constexpr int A2_NA = 6;
#define A2_WPRE 4
#define A2_WLEAD 2
#define A2_RPOS 7
constexpr int A2_SM_A = 10 * WO_STAGE;
constexpr int A2_SM_R = A2_SM_A + A2_NA * 16384;
constexpr int A2_SM_BAR = A2_SM_R + 20480;
constexpr int A2_SMEM = A2_SM_BAR + 256 + 1024;

__global__ void __launch_bounds__(A2_THREADS, 1) a2_kernel(const int layer, const __grid_constant__ CUtensorMap tmO, const __grid_constant__ CUtensorMap tmR,
                                                           const __grid_constant__ CUtensorMap tmX1) {
    extern __shared__ unsigned char smraw[];
    const uint32_t sbase = (smem_u32(smraw) + 1023) & ~1023u;
    const uint32_t bars = sbase + A2_SM_BAR, bar_e = bars + 80, bar_r = bars + 128;
    const int tid = threadIdx.x, w = __shfl_sync(~0u, tid >> 5, 0), wg = w >> 2;
    const int tile = sm_tile();
    if (tile >= 128) { sm_idle(2 * layer + 1); return; }
    const int mb = tile >> 3, cg = tile & 7;
    if (wg == 2) {
        const unsigned char* wsrc = reinterpret_cast<const unsigned char*>(g_wo) + cg * 10 * WO_STAGE;
        if (tid == 256) {
            prefetch_tmap(&tmO);
#pragma unroll
            for (int i = 0; i < 17; i++) mbar_init(bars + 8 * i, i >= 10 && i < 16 ? 2 : 1);
            asm volatile("fence.mbarrier_init.release.cluster;" ::: "memory");
#pragma unroll
            for (int kb = 0; kb < A2_WPRE; kb += 2) {
                mbar_expect_tx(bars + 8 * kb, 16384 + 2 * WO_STAGE);
                bulk_load(sbase + kb * WO_STAGE, wsrc + kb * WO_STAGE, 2 * WO_STAGE, bars + 8 * kb);
            }
        }
        __syncwarp();
        asm volatile("bar.arrive 0, 288;" ::: "memory");
        if (tid == 256) {
#pragma unroll
            for (int kb = 0; kb < 10; kb++) if ((kb & 1) || kb >= A2_WPRE) mbar_expect_tx(bars + 8 * kb, (kb & 1) ? 16384 : 16384 + 2 * WO_STAGE);
            mbar_expect_tx(bar_r, 20480);
            pdl_sync();
#pragma unroll 1
            for (int kb = 0; kb < 10; kb++) {
                if (kb >= A2_NA) mbar_wait(bar_e + 8 * (kb - A2_NA), 0);
                tma_load_2d(sbase + A2_SM_A + (kb < A2_NA ? kb : kb - A2_NA) * 16384, &tmO, kb * 64, mb * 128, bars + 8 * kb);
                const int kw = kb + A2_WLEAD;
                if (!(kw & 1) && kw >= A2_WPRE && kw < 10) bulk_load(sbase + kw * WO_STAGE, wsrc + kw * WO_STAGE, 2 * WO_STAGE, bars + 8 * kw);
                if (kb == A2_RPOS) {
                    if (layer == 0) tma_load_2d(sbase + A2_SM_R, &tmR, cg * 80, mb * 128, bar_r);
                    else { tma_load_2d(sbase + A2_SM_R, &tmR, mb * 128, cg * 80, bar_r); tma_load_2d(sbase + A2_SM_R + 10240, &tmR, mb * 128 + 64, cg * 80, bar_r); }
                }
            }
        }
    } else {
        if (tid == 224) { prefetch_tmap(&tmR); prefetch_tmap(&tmX1); sm_started(2 * layer + 1); }
        asm volatile("bar.sync 0, 288;" ::: "memory");
        SPAN(2 + 4 * layer, 0);
        pdl_sync();
        SPAN(2 + 4 * layer, 1);
        TSTAMP2(0);
        TSTAMP4(0);
        if (threadIdx.x == 0) { GSTAMP(g_tim2, 15); }
        const int lane = tid & 31, warp = w, g = lane >> 2, t = lane & 3;
        const int row = layer * SEQ + mb * 128 + 16 * warp + g;
        const unsigned short pv0 = __ldcg(reinterpret_cast<const unsigned short*>(g_piv) + row), pv1 = __ldcg(reinterpret_cast<const unsigned short*>(g_piv) + row + 8);
        float acc[40];
#pragma unroll
        for (int i = 0; i < 40; i++) acc[i] = 0.f;
        const uint64_t da0 = make_desc(sbase + A2_SM_A + wg * 8192, 16, 1024, 1), db0 = make_desc(sbase, 16, 1024, 1);
#pragma unroll 1
        for (int kb = 0; kb < 10; kb++) {
            if (kb == 0) TSTAMP4(11);
            mbar_wait(bars + 8 * kb, 0);
            TSTAMP4(1 + kb);
            wgmma_fence();
#pragma unroll
            for (int kk = 0; kk < 4; kk++) wgmma_n80<0, 0>(acc, da0 + (uint32_t)((kb < A2_NA ? kb : kb - A2_NA) * 1024 + kk * 2), db0 + (uint32_t)(kb * (WO_STAGE / 16) + kk * 2));
            wgmma_commit();
            wgmma_wait<1>();
            if (kb > 0 && kb <= A2_NA && (tid & 127) == 0) mbar_arrive(bar_e + 8 * (kb - 1));
        }
        const uint32_t trow = ((lane & 7) + 8 * (lane >> 4)) * 128 + (((2 * (warp & 3) + ((lane >> 3) & 1)) ^ (lane & 7)) << 4);
        uint32_t xr[10][2];
        mbar_wait(bar_r, 0);
        if (layer == 0) {
#pragma unroll
            for (int j = 0; j < 10; j += 2) ldsm_x4(&xr[j][0], sbase + A2_SM_R + (16 * warp + (lane & 15)) * 160 + (lane >> 4) * 16 + 16 * j);
        } else {
#pragma unroll
            for (int j = 0; j < 10; j += 2) ldsm_x4_t(&xr[j][0], sbase + A2_SM_R + wg * 10240 + trow + 1024 * j);
        }
        mbar_wait(bar_e + 8 * (4 + wg), 0);
        wgmma_wait<0>();
        TSTAMP2(1);
        const float p0 = __uint_as_float((uint32_t)pv0 << 16), p1 = __uint_as_float((uint32_t)pv1 << 16);
        float s[4] = {0.f, 0.f, 0.f, 0.f};
#pragma unroll
        for (int j = 0; j < 10; j++) {
#pragma unroll
            for (int hh = 0; hh < 2; hh++) {
                const uint32_t a = pack2(acc[4 * j + 2 * hh], acc[4 * j + 2 * hh + 1]);
                const __nv_bfloat162 r = __hadd2_rn(*reinterpret_cast<const __nv_bfloat162*>(&xr[j][hh]), *reinterpret_cast<const __nv_bfloat162*>(&a));
                const uint32_t w = *reinterpret_cast<const uint32_t*>(&r);
                xr[j][hh] = w;
                const float d0 = __uint_as_float(w << 16) - (hh ? p1 : p0), d1 = __uint_as_float(w & 0xffff0000u) - (hh ? p1 : p0);
                s[2 * hh] += d0 + d1;
                s[2 * hh + 1] = fmaf(d0, d0, fmaf(d1, d1, s[2 * hh + 1]));
            }
        }
        const uint32_t so = sbase + A2_SM_A + (4 + wg) * 16384;
#pragma unroll
        for (int j = 0; j < 10; j += 2) stsm_x4_t(so + trow + 1024 * j, xr[j][0], xr[j][1], xr[j + 1][0], xr[j + 1][1]);
        fence_async_smem();
        TSTAMP2(2);
#pragma unroll
        for (int o = 1; o <= 2; o <<= 1)
#pragma unroll
            for (int i = 0; i < 4; i++) s[i] += __shfl_xor_sync(~0u, s[i], o);
        if (t < 2) asm volatile("red.relaxed.gpu.global.add.v2.f32 [%0], {%1, %2};" ::"l"(g_sum + layer * SEQ + (g >> 1) * 512 + (mb * 16 + 2 * warp + t) * 2 + (g & 1)), "f"(t ? s[2] : s[0]), "f"(t ? s[3] : s[1]) : "memory");
        if (wg) asm volatile("bar.sync 2, 128;" ::: "memory"); else asm volatile("bar.sync 1, 128;" ::: "memory");
        TSTAMP2(3);
        if ((tid & 127) == 0) tma_store_2d(&tmX1, mb * 128 + 64 * wg, cg * 80, so);
        TSTAMP2(4);
        GSTAMP(g_tim2, 14);
        SPAN(2 + 4 * layer, 3);
    }
}

static int h_nsm;
static void* h_sym[6];
static CUtensorMap h_tmX0, h_tmX1, h_tmOst, h_tmO, h_tmR0, h_tmR1, h_tmX1st, h_tmOut, h_tmWq, h_tmWo;
typedef CUresult (*PFN_encodeTiled)(CUtensorMap*, CUtensorMapDataType, cuuint32_t, void*, const cuuint64_t*, const cuuint64_t*,
                                    const cuuint32_t*, const cuuint32_t*, CUtensorMapInterleave, CUtensorMapSwizzle,
                                    CUtensorMapL2promotion, CUtensorMapFloatOOBfill);
static void make_tmap(CUtensorMap* tm, const void* ptr, uint64_t cols, uint64_t rows, uint32_t bc, uint32_t br, CUtensorMapSwizzle sw, uint64_t pitch = 0) {
    static PFN_encodeTiled fn = nullptr;
    if (!fn) {
        void* p = nullptr; cudaDriverEntryPointQueryResult qr;
        cudaGetDriverEntryPoint("cuTensorMapEncodeTiled", &p, cudaEnableDefault, &qr);
        fn = (PFN_encodeTiled)p;
    }
    if (br == 0) {
        cuuint64_t dims[4] = {cols, 2, rows / 8, 4}; cuuint64_t strides[3] = {cols * 2, cols * 16, cols * 4};
        cuuint32_t box[4] = {bc, 2, 8, 4}; cuuint32_t es[4] = {1, 1, 1, 1};
        fn(tm, CU_TENSOR_MAP_DATA_TYPE_BFLOAT16, 4, const_cast<void*>(ptr), dims, strides, box, es, CU_TENSOR_MAP_INTERLEAVE_NONE, sw,
           CU_TENSOR_MAP_L2_PROMOTION_L2_128B, CU_TENSOR_MAP_FLOAT_OOB_FILL_NONE);
        return;
    }
    cuuint64_t dims[2] = {cols, rows}; cuuint64_t strides[1] = {(pitch ? pitch : cols) * 2};
    cuuint32_t box[2] = {bc, br}; cuuint32_t es[2] = {1, 1};
    fn(tm, CU_TENSOR_MAP_DATA_TYPE_BFLOAT16, 2, const_cast<void*>(ptr), dims, strides, box, es, CU_TENSOR_MAP_INTERLEAVE_NONE, sw,
       CU_TENSOR_MAP_L2_PROMOTION_L2_128B, CU_TENSOR_MAP_FLOAT_OOB_FILL_NONE);
}
template <typename... Args>
static void launch_pdl(void (*kern)(Args...), int grid, int block, int smem, Args... args) {
    cudaLaunchConfig_t cfg = {};
    cfg.gridDim = dim3(grid); cfg.blockDim = dim3(block); cfg.dynamicSmemBytes = smem; cfg.stream = cudaStreamPerThread;
    cudaLaunchAttribute at[1];
    at[0].id = cudaLaunchAttributeProgrammaticStreamSerialization; at[0].val.programmaticStreamSerializationAllowed = 1;
    cfg.attrs = at; cfg.numAttrs = 1;
    cudaLaunchKernelEx(&cfg, kern, args...);
}
static void launch_stage(int k, void* const* d_in, void* d_out) {
    const KgIn kg = {(const bf16*)d_in[4], (const bf16*)d_in[5], (const bf16*)d_in[6], (const bf16*)d_in[7], (const bf16*)d_in[8], (const bf16*)d_in[0], (const bf16*)d_in[1], (const bf16*)d_in[2],
                      (uint4*)h_sym[0], (uint4*)h_sym[1], (uint4*)h_sym[2], (uint4*)h_sym[3], (uint4*)h_sym[4], (float*)h_sym[5]};
    switch (k) {
        case 0: kgen_kernel<<<DM, KG_THREADS, 0, cudaStreamPerThread>>>(kg, h_tmWq, h_tmWo); break;
        case 1: launch_pdl(a1_kernel, h_nsm, A1_THREADS, A1_SMEM, 0, (const bf16*)d_in[0], h_tmX0, h_tmR1, h_tmOst); break;
        case 2: launch_pdl(a2_kernel, h_nsm, A2_THREADS, A2_SMEM, 0, h_tmO, h_tmR0, h_tmX1st); break;
        case 3: launch_pdl(conv_kernel, DM / CV_CPB, CV_THREADS, CV_SMEM, (const bf16*)d_in[9], 0, h_tmOut); break;
        case 5: launch_pdl(a1_kernel, h_nsm, A1_THREADS, A1_SMEM, 1, (const bf16*)d_in[0], h_tmX1, h_tmR1, h_tmOst); break;
        case 6: launch_pdl(a2_kernel, h_nsm, A2_THREADS, A2_SMEM, 1, h_tmO, h_tmR1, h_tmX1st); break;
        case 7: launch_pdl(conv_kernel, DM / CV_CPB, CV_THREADS, CV_SMEM, (const bf16*)d_in[9], 1, h_tmOut); break;
        default: break;
    }
}
static int n_stage_kernels() { return 9; }
static const char* stage_name(int k) { const char* n[] = {"kgen", "a1", "a2", "conv", "tr", "a1", "a2", "conv", "tr"}; return n[k]; }

extern "C" void kernel_launch(void* const* d_in, const int* in_sizes, int n_in, void* d_out, int out_size) {
    (void)in_sizes; (void)n_in; (void)out_size;
    static const void *p_in = nullptr, *p_w1 = nullptr, *p_w2 = nullptr, *p_out = nullptr;
    if (p_in != d_in[0] || p_w1 != d_in[1] || p_w2 != d_in[2] || p_out != d_out) {
        cudaFuncSetAttribute(conv_kernel, cudaFuncAttributeMaxDynamicSharedMemorySize, CV_SMEM);
        cudaFuncSetAttribute(kgen_kernel, cudaFuncAttributePreferredSharedMemoryCarveout, 100);
        cudaFuncSetAttribute(a1_kernel, cudaFuncAttributeMaxDynamicSharedMemorySize, A1_SMEM);
        cudaFuncSetAttribute(a2_kernel, cudaFuncAttributeMaxDynamicSharedMemorySize, A2_SMEM);
        int dev; cudaGetDevice(&dev); cudaDeviceGetAttribute(&h_nsm, cudaDevAttrMultiProcessorCount, dev);
        if (h_nsm != 132) h_nsm = 128;
        cudaGetSymbolAddress(&h_sym[0], g_tap); cudaGetSymbolAddress(&h_sym[1], g_wq); cudaGetSymbolAddress(&h_sym[2], g_wo);
        cudaGetSymbolAddress(&h_sym[3], g_halo); cudaGetSymbolAddress(&h_sym[4], g_sum); cudaGetSymbolAddress(&h_sym[5], g_csp);
        void *po, *px1, *px2;
        cudaGetSymbolAddress(&po, g_o); cudaGetSymbolAddress(&px1, g_x1T); cudaGetSymbolAddress(&px2, g_xcT);
        make_tmap(&h_tmO, po, 640, 2048, 64, 128, CU_TENSOR_MAP_SWIZZLE_128B);
        make_tmap(&h_tmOst, po, 640, 2048, 80, 16, CU_TENSOR_MAP_SWIZZLE_NONE);
        make_tmap(&h_tmX0, d_in[0], 640, 2048, 64, 128, CU_TENSOR_MAP_SWIZZLE_128B);
        make_tmap(&h_tmX1, px2, 2048, 640, 64, 64, CU_TENSOR_MAP_SWIZZLE_128B, XCP);
        make_tmap(&h_tmR0, d_in[0], 640, 2048, 80, 128, CU_TENSOR_MAP_SWIZZLE_NONE);
        make_tmap(&h_tmR1, px2, 2048, 640, 64, 80, CU_TENSOR_MAP_SWIZZLE_128B, XCP);
        make_tmap(&h_tmX1st, px1, 2048, 640, 64, 80, CU_TENSOR_MAP_SWIZZLE_128B, XCP);
        make_tmap(&h_tmWq, d_in[1], 1920, 640, 32, 0, CU_TENSOR_MAP_SWIZZLE_64B);
        make_tmap(&h_tmWo, d_in[2], 640, 640, 32, 0, CU_TENSOR_MAP_SWIZZLE_64B);
        make_tmap(&h_tmOut, d_out, 640, 2048, 80, 8, CU_TENSOR_MAP_SWIZZLE_NONE);
        p_in = d_in[0]; p_w1 = d_in[1]; p_w2 = d_in[2]; p_out = d_out;
    }
    for (int k = 0; k < n_stage_kernels(); k++) launch_stage(k, d_in, d_out);
}
```

```cpp
#include <cuda_runtime.h>
#include <cuda_bf16.h>
#include <stdint.h>
#include <cuda.h>

typedef __nv_bfloat16 bf16;

constexpr int SEQ = 2048;
constexpr int DM = 640;
constexpr int NMODE = 192;

__device__ __forceinline__ float bf2f(bf16 v) { return __bfloat162float(v); }
__device__ __forceinline__ float rbf(float v) {
    uint32_t r;
    asm("cvt.rn.bf16x2.f32 %0, %1, %2;" : "=r"(r) : "f"(v), "f"(0.f));
    return __uint_as_float(r);
}
__device__ __forceinline__ uint32_t pack2(float lo, float hi) {
    __nv_bfloat162 t = __floats2bfloat162_rn(lo, hi);
    return *reinterpret_cast<uint32_t*>(&t);
}
__device__ __forceinline__ void pdl_sync() {
    asm volatile("griddepcontrol.wait;" ::: "memory");
    asm volatile("griddepcontrol.launch_dependents;" ::: "memory");
}
__device__ __forceinline__ float sqrt_apx(float v) { float r; asm("sqrt.approx.ftz.f32 %0, %1;" : "=f"(r) : "f"(v)); return r; }
__device__ __forceinline__ float rcp_apx(float v) { float r; asm("rcp.approx.ftz.f32 %0, %1;" : "=f"(r) : "f"(v)); return r; }
__device__ __forceinline__ uint32_t smem_u32(const void* p) { return (uint32_t)__cvta_generic_to_shared(p); }

constexpr int TPAD = 16;
constexpr int DLEN = 544;
constexpr int TAP_W2 = DLEN * 8, TAP_W3 = TAP_W2 + 768, TAP_C = TAP_W3 + 768, TAPB = TAP_C + 384;
__device__ __align__(128) uint4 g_tap[DM * 128];
#define XPAD 64
constexpr int XCP = SEQ + XPAD;
__device__ __align__(128) bf16 g_x1T[DM * XCP];
__device__ __align__(128) bf16 g_xcT[DM * XCP];
__device__ __align__(128) bf16 g_o[SEQ * DM];
constexpr int WQ_STAGE = 240 * 128, WO_STAGE = 80 * 128;
__device__ __align__(128) uint4 g_wq[8 * 10 * WQ_STAGE / 16];
__device__ __align__(128) uint4 g_wo[8 * 10 * WO_STAGE / 16];
__device__ __align__(16) float g_csp[10 * 1920];
__device__ __align__(16) float2 g_sum[2 * SEQ];
__device__ __align__(16) bf16 g_piv[2 * SEQ];
__device__ __align__(128) bf16 g_yT[DM * XCP];
__device__ uint32_t g_epoch;
__device__ __align__(16) unsigned long long g_rstat[SEQ];
__device__ ulonglong2 g_part[16 * 8 * 128];
__device__ uint4 g_halo[2 * 128 * 320];
__device__ __forceinline__ unsigned long long tagw(uint32_t payload, uint32_t tag) { return ((unsigned long long)tag << 32) | payload; }
__device__ __forceinline__ void st_tag2(ulonglong2* p, uint32_t a, uint32_t b, uint32_t tag) {
    asm volatile("st.global.cg.v2.u64 [%0], {%1, %2};" ::"l"(p), "l"(tagw(a, tag)), "l"(tagw(b, tag)) : "memory");
}
__device__ __forceinline__ ulonglong2 ld_tag2(const ulonglong2* p) {
    ulonglong2 v;
    asm volatile("ld.relaxed.gpu.global.v2.u64 {%0, %1}, [%2];" : "=l"(v.x), "=l"(v.y) : "l"(p) : "memory");
    return v;
}
__device__ __forceinline__ bool tag_ok(ulonglong2 v, uint32_t tag) { return (uint32_t)(v.x >> 32) == tag && (uint32_t)(v.y >> 32) == tag; }
__device__ __forceinline__ uint32_t ld_epoch() { uint32_t v; asm volatile("ld.relaxed.gpu.global.u32 %0, [%1];" : "=r"(v) : "l"(&g_epoch) : "memory"); return v + 1; }
constexpr int SPIN_MAX = 1 << 20;
__device__ uint32_t g_started[4];
__device__ __forceinline__ void sm_started(int slot) { asm volatile("red.relaxed.gpu.global.add.u32 [%0], 1;" ::"l"(g_started + slot) : "memory"); }
__device__ __noinline__ void sm_idle(int slot) {
    if (threadIdx.x) return;
    sm_started(slot);
    const uint32_t want = ld_epoch() * gridDim.x;
    pdl_sync();
#pragma unroll 1
    for (int it = 0; it < SPIN_MAX; it++) {
        uint32_t v;
        asm volatile("ld.relaxed.gpu.global.u32 %0, [%1];" : "=r"(v) : "l"(g_started + slot) : "memory");
        if ((int)(v - want) >= 0) break;
        __nanosleep(100);
    }
}
__device__ __forceinline__ int sm_tile() {
    uint32_t s;
    asm volatile("mov.u32 %0, %smid;" : "=r"(s));
    const uint32_t h = (s - 64) >> 1, q = (h * 37) >> 8;
    const int t0 = ((s >> 1) & 7) * 16 + (s >> 4) * 2 + (s & 1), t1 = (1 + h - 7 * q) * 16 + 8 + q * 2 + (s & 1), t2 = s - 124 < 8 ? s - 116 : 128;
    return gridDim.x == 128 ? (int)blockIdx.x : s < 64 ? t0 : s < 120 ? t1 : t2;
}
#define DBG_SYMS
#define TSTAMP(i)
#define TSTAMP1(i)
#define TSTAMP1T(i, t)
#define TSTAMP1X(i, t)
#define SPAN(k, i)
#define GSTAMP(arr, i)
#define TSTAMP2(i)
#define TSTAMP3(i)
#define TSTAMP4(i)
#define TSTAMPK(i, t)

__device__ __forceinline__ void mma_bf16(float* d, uint32_t a0, uint32_t a1, uint32_t a2, uint32_t a3, uint32_t b0, uint32_t b1) {
    asm volatile("mma.sync.aligned.m16n8k16.row.col.f32.bf16.bf16.f32 {%0,%1,%2,%3}, {%4,%5,%6,%7}, {%8,%9}, {%0,%1,%2,%3};"
                 : "+f"(d[0]), "+f"(d[1]), "+f"(d[2]), "+f"(d[3]) : "r"(a0), "r"(a1), "r"(a2), "r"(a3), "r"(b0), "r"(b1));
}
__device__ __forceinline__ void mma_bf16_k8(float* d, uint32_t a0, uint32_t a1, uint32_t b0) {
    asm volatile("mma.sync.aligned.m16n8k8.row.col.f32.bf16.bf16.f32 {%0,%1,%2,%3}, {%4,%5}, {%6}, {%0,%1,%2,%3};"
                 : "+f"(d[0]), "+f"(d[1]), "+f"(d[2]), "+f"(d[3]) : "r"(a0), "r"(a1), "r"(b0));
}
__device__ __forceinline__ void ldsm_x4(uint32_t* r, uint32_t addr) {
    asm volatile("ldmatrix.sync.aligned.m8n8.x4.shared.b16 {%0,%1,%2,%3}, [%4];"
                 : "=r"(r[0]), "=r"(r[1]), "=r"(r[2]), "=r"(r[3]) : "r"(addr));
}

__device__ __forceinline__ void ldsm_x4_t(uint32_t* r, uint32_t addr) {
    asm volatile("ldmatrix.sync.aligned.m8n8.x4.trans.shared.b16 {%0,%1,%2,%3}, [%4];"
                 : "=r"(r[0]), "=r"(r[1]), "=r"(r[2]), "=r"(r[3]) : "r"(addr));
}
__device__ __forceinline__ void mbar_init(uint32_t bar, int count) { asm volatile("mbarrier.init.shared::cta.b64 [%0], %1;" ::"r"(bar), "r"(count)); }
__device__ __forceinline__ void mbar_arrive(uint32_t bar) { asm volatile("mbarrier.arrive.shared::cta.b64 _, [%0];" ::"r"(bar) : "memory"); }
__device__ __forceinline__ void mbar_wait(uint32_t bar, uint32_t parity) {
    asm volatile("{\n.reg .pred p;\nWAIT_LOOP:\n"
                 "mbarrier.try_wait.parity.shared::cta.b64 p, [%0], %1;\n"
                 "@p bra.uni WAIT_DONE;\nbra.uni WAIT_LOOP;\nWAIT_DONE:\n}" ::"r"(bar), "r"(parity) : "memory");
}

__device__ __forceinline__ void mbar_expect_tx(uint32_t bar, uint32_t bytes) {
    asm volatile("mbarrier.arrive.expect_tx.shared::cta.b64 _, [%0], %1;" ::"r"(bar), "r"(bytes) : "memory");
}
__device__ __forceinline__ void tma_load_2d(uint32_t dst, const void* tmap, int c0, int c1, uint32_t bar) {
    asm volatile("cp.async.bulk.tensor.2d.shared::cluster.global.mbarrier::complete_tx::bytes [%0], [%1, {%3, %4}], [%2];"
                 ::"r"(dst), "l"(tmap), "r"(bar), "r"(c0), "r"(c1) : "memory");
}
__device__ __forceinline__ void fence_async_smem() { asm volatile("fence.proxy.async.shared::cta;" ::: "memory"); }
__device__ __forceinline__ void bulk_load(uint32_t dst, const void* src, uint32_t bytes, uint32_t bar) {
    asm volatile("cp.async.bulk.shared::cluster.global.mbarrier::complete_tx::bytes [%0], [%1], %2, [%3];"
                 ::"r"(dst), "l"(src), "r"(bytes), "r"(bar) : "memory");
}
__device__ __forceinline__ void tma_store_2d(const void* tmap, int c0, int c1, uint32_t src) {
    asm volatile("cp.async.bulk.tensor.2d.global.shared::cta.bulk_group [%0, {%1, %2}], [%3];" ::"l"(tmap), "r"(c0), "r"(c1), "r"(src) : "memory");
    asm volatile("cp.async.bulk.commit_group;" ::: "memory");
    asm volatile("cp.async.bulk.wait_group.read 0;" ::: "memory");
}
__device__ __forceinline__ void stsm_x4(uint32_t addr, uint32_t r0, uint32_t r1, uint32_t r2, uint32_t r3) {
    asm volatile("stmatrix.sync.aligned.m8n8.x4.shared.b16 [%0], {%1,%2,%3,%4};" ::"r"(addr), "r"(r0), "r"(r1), "r"(r2), "r"(r3) : "memory");
}
__device__ __forceinline__ void stsm_x4_t(uint32_t addr, uint32_t r0, uint32_t r1, uint32_t r2, uint32_t r3) {
    asm volatile("stmatrix.sync.aligned.m8n8.x4.trans.shared.b16 [%0], {%1,%2,%3,%4};" ::"r"(addr), "r"(r0), "r"(r1), "r"(r2), "r"(r3) : "memory");
}
__device__ __forceinline__ void prefetch_tmap(const void* tmap) { asm volatile("prefetch.tensormap [%0];" ::"l"(tmap) : "memory"); }

__device__ __forceinline__ float2 cexp_at(float wr2, float wi, float p) {
    float er;
    asm("ex2.approx.ftz.f32 %0, %1;" : "=f"(er) : "f"(wr2 * p));
    float th = wi * p;
    const float k = rintf(th * 0.15915494309189535f);
    th = fmaf(k, -6.2831854820251465f, th);
    th = fmaf(k, 1.7484555314695172e-7f, th);
    return make_float2(er * __cosf(th), er * __sinf(th));
}
__device__ __forceinline__ float2 cmul(float2 a, float2 b) {
    return make_float2(fmaf(a.x, b.x, -a.y * b.y), fmaf(a.x, b.y, a.y * b.x));
}
__device__ __forceinline__ float2 csqr(float2 a) { return make_float2(fmaf(a.x, a.x, -a.y * a.y), (a.x + a.x) * a.y); }
__device__ __forceinline__ uint32_t packh(float2 v) {
    uint32_t r;
    asm("cvt.rn.f16x2.f32 %0, %1, %2;" : "=r"(r) : "f"(v.y), "f"(v.x));
    return r;
}
__device__ __forceinline__ void mma_f16(float* d, uint32_t a0, uint32_t a1, uint32_t a2, uint32_t a3, uint32_t b0, uint32_t b1) {
    asm volatile("mma.sync.aligned.m16n8k16.row.col.f32.f16.f16.f32 {%0,%1,%2,%3}, {%4,%5,%6,%7}, {%8,%9}, {%0,%1,%2,%3};"
                 : "+f"(d[0]), "+f"(d[1]), "+f"(d[2]), "+f"(d[3]) : "r"(a0), "r"(a1), "r"(a2), "r"(a3), "r"(b0), "r"(b1));
}

struct KgIn { const bf16 *logA, *Aim, *Cre, *Cim, *logdt, *x, *wqkv, *wo; uint4 *tap, *wq, *wop, *halo, *sum; float* csp; };
constexpr int KG_THREADS = NMODE / 2;

__global__ void __launch_bounds__(KG_THREADS, 5) kgen_kernel(const KgIn in, const __grid_constant__ CUtensorMap tmWq, const __grid_constant__ CUtensorMap tmWo) {
    __shared__ __align__(8) unsigned long long wbar[3];
    __shared__ __align__(1024) uint4 tab[3 * 896];
    const int d = blockIdx.x, tid = threadIdx.x, lane = tid & 31, warp = __shfl_sync(~0u, tid >> 5, 0);
    SPAN(0, 0); SPAN(0, 1);
    TSTAMPK(0, 0);
    asm volatile("griddepcontrol.launch_dependents;" ::: "memory");
    const bf16 pdt = in.logdt[d];
    const uint32_t pla = reinterpret_cast<const uint32_t*>(in.logA)[d * KG_THREADS + tid], pai = reinterpret_cast<const uint32_t*>(in.Aim)[d * KG_THREADS + tid];
    const uint32_t pcr = reinterpret_cast<const uint32_t*>(in.Cre)[d * KG_THREADS + tid], pci = reinterpret_cast<const uint32_t*>(in.Cim)[d * KG_THREADS + tid];
    const bf16* pfq = tid < 30 ? in.wqkv + (size_t)(d * 30 + tid) * 64 : tid < 40 ? in.wo + (size_t)(d * 10 + tid - 30) * 64 : in.x + (size_t)(d * 32 + tid - 40) * 64;
    if (tid < 72) asm volatile("prefetch.global.L2 [%0];" ::"l"(pfq));
    asm volatile("st.global.v4.u32 [%0], {%1,%1,%1,%1};" ::"l"(in.halo + d * 128 + tid), "r"(~0u));
    if (tid < 32) asm volatile("st.global.v4.u32 [%0], {%1,%1,%1,%1};" ::"l"(in.halo + d * 128 + 96 + tid), "r"(~0u));
    const uint32_t tw = smem_u32(tab) + warp * 14336;
    if (lane == 0) { mbar_init(smem_u32(wbar + warp), 1); prefetch_tmap(d >= 200 ? &tmWo : &tmWq); }
    const int g = lane >> 2, t = lane & 3;
    const uint32_t sta = tw + lane * 128 + ((2 * (lane & 3) + ((lane >> 2) & 1)) << 4);
    const uint32_t lda = tw + t * 128 + ((g ^ (2 * t)) << 4);
    const uint32_t stb = tw + 12288 + lane * 64 + ((4 * ((lane >> 1) & 1) + ((lane >> 2) & 3)) << 3);
    const uint32_t ldb = tw + 12288 + t * 64 + ((g ^ (4 * (t >> 1))) << 3);
    auto sts4 = [&](int e, int off, uint32_t a, uint32_t b, uint32_t c, uint32_t dd) {
        asm volatile("st.shared.v4.u32 [%0], {%1,%2,%3,%4};" ::"r"((sta ^ (e << 4)) + off), "r"(a), "r"(b), "r"(c), "r"(dd) : "memory");
    };
    auto lds4 = [&](int sp, int off, uint32_t* r) {
        asm volatile("ld.shared.v4.u32 {%0,%1,%2,%3}, [%4];" : "=r"(r[0]), "=r"(r[1]), "=r"(r[2]), "=r"(r[3]) : "r"((lda ^ ((sp & 1) << 4)) + sp * 512 + off) : "memory");
    };
    const float dt = rbf(expf(bf2f(pdt)));
    float2 C[2], y1[2], z8[2], y128[2];
    float cmax = 0.f;
#pragma unroll
    for (int m = 0; m < 2; m++) {
        const float wr2 = -rbf(expf(__uint_as_float(m ? pla & 0xffff0000u : pla << 16))) * dt * 1.4426950408889634f;
        const float wi = __uint_as_float(m ? pai & 0xffff0000u : pai << 16) * dt;
        C[m] = make_float2(__uint_as_float(m ? pcr & 0xffff0000u : pcr << 16) * dt, -__uint_as_float(m ? pci & 0xffff0000u : pci << 16) * dt);
        cmax = fmaxf(cmax, fmaxf(fabsf(C[m].x), fabsf(C[m].y)));
        y1[m] = cexp_at(wr2, -wi, 1.f); z8[m] = cexp_at(wr2, wi, 8.f); y128[m] = cexp_at(wr2, -wi, 128.f);
    }
    const int ex = min(max((int)(__reduce_max_sync(~0u, __float_as_uint(cmax)) >> 23), 20), 240);
    const float scale = __uint_as_float((uint32_t)(127 + 10 + 127 - ex) << 23), unscale = 2.0f * __uint_as_float((uint32_t)(ex - 10) << 23);
    TSTAMPK(4, 0);
    float k2048 = 0.f;
    float acc[5][4];
#pragma unroll
    for (int j = 0; j < 5; j++)
#pragma unroll
        for (int k = 0; k < 4; k++) acc[j][k] = 0.f;
    uint32_t af[8][4];
    {
        float2 h0[2], h1[2], g0[2], g1[2], g2[2], g2b[2], g3[2], g4[2], y2[2], y4[2];
#pragma unroll
        for (int m = 0; m < 2; m++) {
            h0[m] = make_float2(1.f, 0.f); h1[m] = csqr(csqr(csqr(z8[m])));
            g0[m] = make_float2(C[m].x * scale, C[m].y * scale);
            g1[m] = cmul(g0[m], y128[m]);
            const float2 y256 = csqr(y128[m]), y512 = csqr(y256);
            g2b[m] = g2[m] = cmul(g0[m], y256); g3[m] = cmul(g0[m], y512); g4[m] = cmul(g3[m], y512);
            y2[m] = csqr(y1[m]); y4[m] = csqr(y2[m]);
            const float2 y1024 = csqr(y512);
            k2048 += fmaf(g4[m].x, y1024.x, -g4[m].y * y1024.y);
        }
#pragma unroll
        for (int e = 0; e < 8; e++) {
            sts4(e, 0, packh(h0[0]), packh(h1[0]), packh(h0[1]), packh(h1[1]));
            sts4(e, 4096, packh(g0[0]), packh(g0[1]), packh(g1[0]), packh(g1[1]));
#pragma unroll
            for (int m = 0; m < 2; m++)
                if (e < 7) { h0[m] = e ? cmul(h0[m], z8[m]) : z8[m]; h1[m] = cmul(h1[m], z8[m]); g0[m] = cmul(g0[m], y1[m]); g1[m] = cmul(g1[m], y1[m]); }
            if (e < 5) k2048 += __shfl_xor_sync(~0u, k2048, 1 << e);
        }
        __syncwarp();
#pragma unroll
        for (int e = 0; e < 8; e++) {
            uint32_t b[4];
            lds4(e, 0, af[e]); lds4(e, 4096, b);
            sts4(e, 8192, packh(g2[0]), packh(g2[1]), packh((e & 1) ? cmul(g3[0], y4[0]) : g3[0]), packh((e & 1) ? cmul(g3[1], y4[1]) : g3[1]));
            asm volatile("st.shared.v2.u32 [%0], {%1,%2};" ::"r"(stb ^ (e << 3)), "r"(packh(g4[0])), "r"(packh(g4[1])) : "memory");
#pragma unroll
            for (int m = 0; m < 2; m++)
                if (e < 7) {
                    g2[m] = e == 3 ? cmul(g2b[m], y128[m]) : cmul(g2[m], y2[m]);
                    if (e & 1) g3[m] = cmul(g3[m], y128[m]);
                    g4[m] = cmul(g4[m], y128[m]);
                }
            mma_f16(acc[0], af[e][0], af[e][1], af[e][2], af[e][3], b[0], b[1]);
            mma_f16(acc[1], af[e][0], af[e][1], af[e][2], af[e][3], b[2], b[3]);
        }
    }
    TSTAMPK(6, 0);
    const int job = d * 3 + warp;
    const bool isq = job < 600;
    const int j2 = isq ? job : job - 600, scol = (j2 / 10) * 32, skb = j2 - (j2 / 10) * 10;
    fence_async_smem();
    __syncwarp();
    if (job < 800) {
        if (lane == 0) {
            mbar_expect_tx(smem_u32(wbar + warp), 4096);
            asm volatile("cp.async.bulk.tensor.4d.shared::cluster.global.mbarrier::complete_tx::bytes [%0], [%1, {%3, %4, %5, %4}], [%2];"
                         ::"r"(tw + 4096), "l"(isq ? &tmWq : &tmWo), "r"(smem_u32(wbar + warp)), "r"(scol), "r"(0), "r"(skb * 8) : "memory");
        }
    } else if (job < 800 + 64) in.sum[(job - 800) * 32 + lane] = make_uint4(0, 0, 0, 0);
#pragma unroll
    for (int sp = 0; sp < 8; sp++) {
        uint32_t c[4], e0, e1;
        lds4(sp, 8192, c);
        asm volatile("ld.shared.v2.u32 {%0,%1}, [%2];" : "=r"(e0), "=r"(e1) : "r"((ldb ^ ((sp & 3) << 3)) + sp * 256) : "memory");
        mma_f16(acc[2], af[sp][0], af[sp][1], af[sp][2], af[sp][3], c[0], c[1]);
        mma_f16(acc[3], af[sp][0], af[sp][1], af[sp][2], af[sp][3], c[2], c[3]);
        mma_f16(acc[4], af[sp][0], af[sp][1], af[sp][2], af[sp][3], e0, e1);
    }
    {
        float* Pp = reinterpret_cast<float*>(tab + warp * 896);
#pragma unroll
        for (int h = 0; h < 2; h++) {
            const int b = g + 8 * h;
            *reinterpret_cast<float2*>(Pp + 8 * b + 2 * t) = make_float2(acc[0][2 * h] * unscale, acc[0][2 * h + 1] * unscale);
            *reinterpret_cast<float2*>(Pp + 128 + 8 * b + 2 * t) = make_float2(acc[1][2 * h] * unscale, acc[1][2 * h + 1] * unscale);
            *reinterpret_cast<float2*>(Pp + 256 + 4 * b + 2 * (t & 1) + 64 * (t >> 1)) = make_float2(acc[2][2 * h] * unscale, acc[2][2 * h + 1] * unscale);
            *reinterpret_cast<float2*>(Pp + 384 + 2 * b + 32 * t) = make_float2(acc[3][2 * h] * unscale, acc[3][2 * h + 1] * unscale);
            Pp[512 + b + 32 * t] = acc[4][2 * h] * unscale;
            Pp[512 + b + 32 * t + 16] = acc[4][2 * h + 1] * unscale;
        }
        if (lane == 0) Pp[640] = k2048 * unscale;
    }
    TSTAMPK(7, 0);
    __syncthreads();
    TSTAMPK(9, 0);
    const float* Kp = reinterpret_cast<const float*>(tab);
    auto ksum = [&](int i) -> float { return (Kp[i] + Kp[3584 + i]) + Kp[7168 + i]; };
    auto ksum4 = [&](int q) -> float4 {
        const float4 a = reinterpret_cast<const float4*>(Kp)[q], b = reinterpret_cast<const float4*>(Kp)[896 + q], c = reinterpret_cast<const float4*>(Kp)[1792 + q];
        return make_float4((a.x + b.x) + c.x, (a.y + b.y) + c.y, (a.z + b.z) + c.z, (a.w + b.w) + c.w);
    };
    {
        uint2* E4 = reinterpret_cast<uint2*>(in.tap + d * 128);
        float4 v = ksum4(tid), u = ksum4(96 + min(tid, 64));
        const float cor = rbf(ksum(tid == 95 ? 384 : 512));
        if (tid == 95) v.w -= cor;
        if (tid == 31) u.w -= cor;
        const uint32_t lo = pack2(v.x, v.y), hi = pack2(v.z, v.w);
        if (tid < 64) {
            E4[6 + tid] = make_uint2(lo, hi);
            E4[(tid < 32 ? 159 : 209 - 32) + tid] = make_uint2(pack2(u.x, u.y), pack2(u.z, u.w));
        } else {
            const uint32_t nx = __shfl_down_sync(~0u, lo, 1);
            in.tap[d * 128 + 35 + tid - 64] = make_uint4(__byte_perm(lo, 0, 0x1010), __byte_perm(lo, hi, 0x5432), __byte_perm(hi, 0, 0x1010), __byte_perm(hi, tid == 95 ? 0u : nx, 0x5432));
            if (tid == 64) E4[241] = make_uint2(pack2(u.x, 0.f), 0u);
        }
    }
    TSTAMPK(10, 0);
    if (job < 800) {
        mbar_wait(smem_u32(wbar + warp), 0);
        const uint32_t src = tw + 4096 + ((lane >> 3) * 16 + (lane & 7)) * 64;
#pragma unroll
        for (int cg = 0; cg < 4; cg++) {
            const int col = scol + 8 * cg, sec = col / DM, r = col - sec * DM, hg = r / 80;
            const int n = isq ? hg * 160 + sec * 80 + r : col;
            unsigned char* dst = (isq ? reinterpret_cast<unsigned char*>(in.wq) + (hg * 9 + skb) * WQ_STAGE : reinterpret_cast<unsigned char*>(in.wop) + (hg * 9 + skb) * WO_STAGE) + (n + g) * 128;
            float cs[4] = {0.f, 0.f, 0.f, 0.f};
#pragma unroll
            for (int h = 0; h < 2; h++) {
                uint32_t w[4];
                ldsm_x4_t(w, src + h * 512 + ((cg ^ ((lane >> 1) & 3)) << 4));
                *reinterpret_cast<uint4*>(dst + (((4 * h + t) ^ g) << 4)) = make_uint4(w[0], w[1], w[2], w[3]);
                if (isq) {
                    mma_bf16(cs, 0x3f803f80u, 0u, 0x3f803f80u, 0u, w[0], w[1]);
                    mma_bf16(cs, 0x3f803f80u, 0u, 0x3f803f80u, 0u, w[2], w[3]);
                }
            }
            if (isq && g == cg) *reinterpret_cast<float2*>(in.csp + skb * 1920 + n + 2 * t) = make_float2(cs[0], cs[1]);
        }
    }
    TSTAMPK(11, 0);
    SPAN(0, 3);
}

#define CV_MODE 0
#define CV_SLEEP 100
constexpr int CV_CPB = 5;
constexpr int CV_THREADS = 512;
constexpr int UPADF = 128;
constexpr int ULEN = UPADF + SEQ + 80;
constexpr int XLEN = SEQ + 16;
constexpr int BX_5 = 0, BX_3 = 3264, BX_9 = 6528, BX_7 = 8960, BX_LEN = 11392;
constexpr int CV_SM_T = 0;
constexpr int CV_SM_B = CV_CPB * TAPB;
constexpr int CV_SM_U = CV_SM_B + CV_CPB * BX_LEN;
constexpr int CV_SM_X = CV_SM_U + CV_CPB * ULEN * 2;
constexpr int CV_SM_Y = CV_SM_X + CV_CPB * XLEN * 2;
constexpr int CV_SM_P = CV_SM_Y + CV_CPB * XLEN * 2;
constexpr int CV_SM_CNT = CV_SM_P + 6 * 4096;
constexpr int CV_SM_O = (CV_SM_CNT + 128 + 127) & ~127;
constexpr int CV_SMEM = CV_SM_O + 20480;
static_assert(CV_SM_B % 128 == 0 && CV_SM_CNT % 16 == 0, "layout");

__device__ __forceinline__ uint32_t ln2(uint32_t x, uint32_t m, float ra, float rb) {
    const __nv_bfloat162 d = __hsub2(*reinterpret_cast<const __nv_bfloat162*>(&x), *reinterpret_cast<const __nv_bfloat162*>(&m));
    const uint32_t w = *reinterpret_cast<const uint32_t*>(&d);
    return pack2(__uint_as_float(w << 16) * ra, __uint_as_float(w & 0xffff0000u) * rb);
}
__device__ __forceinline__ void cp_async16(uint32_t dst, const void* src) {
    asm volatile("cp.async.cg.shared.global [%0], [%1], 16;" ::"r"(dst), "l"(src));
}
__device__ __forceinline__ void cp_async_wait_all() { asm volatile("cp.async.wait_all;" ::: "memory"); }

template <bool FULL>
__device__ __forceinline__ void direct_pass(float (&acc)[8][4], uint32_t ub, uint32_t o0, uint32_t o1, const uint2* __restrict__ Tp, bool first_half) {
    uint32_t sw[8][8];
#pragma unroll
    for (int j = 0; j < 8; j++) { ldsm_x4(&sw[j][0], ub + o0 + j * 256); ldsm_x4(&sw[j][4], ub + o1 + j * 256); }
#pragma unroll
    for (int M = 0; M < 4; M++) {
#pragma unroll
        for (int i = 0; i < 4; i++) {
            const uint2 hi = Tp[128 * M + 16 * i], lo = Tp[128 * M + 16 * i - 8];
#pragma unroll
            for (int j = FULL ? 0 : M; j < 8; j++) mma_bf16(acc[j], hi.x, hi.y, lo.x, lo.y, sw[(j - M) & 7][2 * i], sw[(j - M) & 7][2 * i + 1]);
        }
        if (FULL) {
            ldsm_x4(&sw[7 - M][0], ub + o0 - (M + 1) * 256);
            if (M < 3) ldsm_x4(&sw[7 - M][4], ub + o1 - (M + 1) * 256);
        }
    }
    if (first_half) {
        const uint2 hi = Tp[512], lo = Tp[504];
#pragma unroll
        for (int j = FULL ? 0 : 4; j < 8; j++) mma_bf16(acc[j], hi.x, hi.y, lo.x, lo.y, sw[(j - 4) & 7][0], sw[(j - 4) & 7][1]);
    }
}
__device__ __forceinline__ uint32_t fin2(uint32_t x, uint32_t y, uint32_t u, uint32_t dk) {
    typedef __nv_bfloat162 b2;
    const b2 r = __hadd2_rn(*reinterpret_cast<const b2*>(&x), __hadd2_rn(*reinterpret_cast<const b2*>(&y),
                            __hmul2_rn(*reinterpret_cast<const b2*>(&u), *reinterpret_cast<const b2*>(&dk))));
    return *reinterpret_cast<const uint32_t*>(&r);
}
__global__ void __launch_bounds__(CV_THREADS, 1) conv_kernel(const bf16* __restrict__ Dskip, int layer, const __grid_constant__ CUtensorMap tmOut) {
    extern __shared__ __align__(128) unsigned char sm[];
    SPAN(3 + 4 * layer, 0);
    bf16* Us = reinterpret_cast<bf16*>(sm + CV_SM_U);
    bf16* Xs = reinterpret_cast<bf16*>(sm + CV_SM_X);
    bf16* Ys = reinterpret_cast<bf16*>(sm + CV_SM_Y);
    const int tid = threadIdx.x, lane = tid & 31, warp = __shfl_sync(~0u, tid >> 5, 0);
    const int d0 = blockIdx.x * CV_CPB, tile = blockIdx.x; (void)tile;
    const int g = lane >> 2, ti = lane & 3;
    const int e = g - 2 * ti;
    uint32_t lds_off[4];
    uint32_t off2, off3, offc;
    {
        const int mat = lane >> 3, r = lane & 7;
#pragma unroll
        for (int pr = 0; pr < 4; pr++) {
            const int iw = 2 * pr + (mat >> 1), half = mat & 1;
            const int chunk = (UPADF - 16 * iw + 16 * r + 8 * half) >> 3;
            lds_off[pr] = (uint32_t)((chunk ^ ((chunk >> 3) & 1)) * 16);
        }
        const int j2 = 13 + r + 8 * (mat >> 1), j3 = j2 + 2, i0 = 8 * (mat & 1);
        off2 = (j2 & 1) ? BX_3 + (4 * j2 + i0 + 84) * 2 : BX_5 + (4 * j2 + i0 + 80) * 2;
        off3 = ((j3 & 1) ? BX_7 : BX_9) + (8 * j3 + i0 + 136) * 2;
        const int cc = (UPADF + 16 * (r + (mat >> 1)) + i0) >> 3;
        offc = (uint32_t)((cc ^ ((cc >> 3) & 1)) * 16);
    }
    const uint32_t rtab = warp < 8 ? (warp < 4 ? 0x0B090200u : 0x0C0A0301u) : (warp < 12 ? 0x13111008u : 0x1412241Cu);
    const int rl = (rtab >> (8 * (warp & 3))) & 0xff, type = rl >> 3, c = rl & 7;
    const int H = (type == 1 || type == 2) ? 1 : 0, T0 = 8 * H;
    uint32_t toff = CV_SM_T + c * TAPB + (TPAD + e) * 8;
    uint32_t ubase = smem_u32(Us + c * ULEN);
    const uint32_t bbase = smem_u32(sm + CV_SM_B + c * BX_LEN);
    uint32_t rd0, rd1;
    {
        const uint32_t rstart = warp < 8 ? (warp < 4 ? 0x02000000u : 0x06040000u) : (warp < 12 ? 0x0C0B0A08u : 0x1E1D150Fu);
        const uint32_t rcount = warp < 8 ? 0x02020000u : (warp < 12 ? 0x03010102u : 0x01010806u);
        rd0 = (rstart >> (8 * (warp & 3))) & 0xff; rd1 = rd0 + ((rcount >> (8 * (warp & 3))) & 0xff);
    }
    asm volatile("" : "+r"(lds_off[0]), "+r"(lds_off[1]), "+r"(lds_off[2]), "+r"(lds_off[3]), "+r"(ubase), "+r"(toff), "+r"(rd0), "+r"(rd1));
    const uint2* Tc = reinterpret_cast<const uint2*>(sm + toff);
    TSTAMP1X(9, 256);
    unsigned short dskr;
    asm volatile("ld.global.nc.u16 %0, [%1];" : "=h"(dskr) : "l"(Dskip + d0 + min(lane, CV_CPB - 1)));
    if (tid >= 256) {
        const int t2 = tid - 256;
        if (t2 == 0) {
            mbar_init(smem_u32(sm + CV_SM_CNT) + 104, 1);
            asm volatile("fence.mbarrier_init.release.cluster;" ::: "memory");
            mbar_expect_tx(smem_u32(sm + CV_SM_CNT) + 104, CV_CPB * 2048);
            bulk_load(smem_u32(sm + CV_SM_O), g_tap + d0 * 128, CV_CPB * 2048, smem_u32(sm + CV_SM_CNT) + 104);
        } else if (lane == 0) {
            mbar_init(smem_u32(sm + CV_SM_CNT) + 16 * (warp - 9), warp == 15 ? 16 : 1);
            if (warp < 15) mbar_init(smem_u32(sm + CV_SM_CNT) + 16 * (warp - 9) + 8, 1);
            else if (layer) prefetch_tmap(&tmOut);
        }
        if (t2 < 149) {
            const int k = t2;
            const int off = k < 18 ? BX_5 + 8 * k : k < 37 ? BX_3 + 8 * (k - 18) : k < 69 ? BX_9 + 8 * (k - 37) : k < 101 ? BX_7 + 8 * (k - 69)
                          : k < 133 ? 8 * (k - 101) : (UPADF + SEQ) * 2 + 8 * (k - 133);
#pragma unroll
            for (int c = 0; c < CV_CPB; c++) *reinterpret_cast<uint2*>(sm + (k < 101 ? CV_SM_B + c * BX_LEN : CV_SM_U + c * ULEN * 2) + off) = make_uint2(0, 0);
        }
        asm volatile("bar.sync 1, 256;" ::: "memory");
        TSTAMP1X(10, 256);
        mbar_wait(smem_u32(sm + CV_SM_CNT) + 104, 0);
        TSTAMP1X(11, 256);
#pragma unroll 1
        for (int r = t2; r < 392; r += 256) {
            const bool dd = r < 272, cc = r >= 368;
            const uint32_t* E2 = reinterpret_cast<const uint32_t*>(sm + CV_SM_O) + (dd ? r + 3 : r < 320 ? 301 + 2 * (r - 272) : cc ? 417 : 401 + 2 * (r - 320));
            const uint32_t* E3 = E2 + (dd ? 4 : cc ? 0 : 1);
            const uint32_t s0 = !cc ? 0x7610u : r == 382 ? 0x1044u : 0x4444u, s1 = !cc ? 0x7610u : r == 378 ? 0x1044u : 0x4444u;
            const uint32_t s2 = !cc ? 0x1032u : r == 381 ? 0x4410u : 0x4444u, s3 = !cc ? 0x1032u : r == 377 ? 0x4410u : 0x4444u;
            uint32_t w[CV_CPB][4];
#pragma unroll
            for (int c = 0; c < CV_CPB; c++) { w[c][0] = E2[512 * c]; w[c][1] = E2[512 * c + 1]; w[c][2] = E3[512 * c]; w[c][3] = E3[512 * c + 1]; }
#pragma unroll
            for (int c = 0; c < CV_CPB; c++) {
                const uint32_t a = __byte_perm(w[c][3], w[c][2], s1), b = __byte_perm(w[c][1], w[c][0], s2);
                *reinterpret_cast<uint4*>(sm + CV_SM_T + c * TAPB + r * 16) =
                    make_uint4(__byte_perm(w[c][1], w[c][0], s0), dd || cc ? a : b, dd || cc ? b : a, __byte_perm(w[c][3], w[c][2], s3));
            }
        }
        TSTAMP1X(12, 256);
        if (layer == 0) {
#pragma unroll
            for (int c = 0; c < CV_CPB; c++) reinterpret_cast<uint4*>(g_yT + (size_t)(d0 + c) * XCP)[t2] = make_uint4(~0u, ~0u, ~0u, ~0u);
        }
        pdl_sync();
        if (layer && blockIdx.x == 0 && t2 == 0) g_epoch = ld_epoch();
    } else {
        const uint4* ppv = reinterpret_cast<const uint4*>(g_piv + layer * SEQ) + tid;
        const float4* psv = reinterpret_cast<const float4*>(g_sum + layer * SEQ) + tid;
        const uint4* pxv = reinterpret_cast<const uint4*>(g_x1T + (size_t)d0 * XCP) + tid;
        asm volatile("" : "+l"(ppv), "+l"(psv), "+l"(pxv));
        pdl_sync();
        SPAN(3 + 4 * layer, 1);
        TSTAMP(0);
        if (threadIdx.x == 0) { GSTAMP(g_tim, 15); }
        float4 sv[4];
#pragma unroll
        for (int k = 0; k < 4; k++) sv[k] = __ldcg(psv + 256 * k);
        const uint4 pv = __ldcg(ppv);
        uint4 xv[CV_CPB];
#pragma unroll
        for (int c = 0; c < CV_CPB; c++) xv[c] = __ldcg(pxv + c * (XCP / 8));
        uint32_t mw[4];
        float rs[8];
#pragma unroll
        for (int k = 0; k < 4; k++) {
            const uint32_t pw = k == 0 ? pv.x : k == 1 ? pv.y : k == 2 ? pv.z : pv.w;
            const float d0_ = sv[k].x * (1.0f / DM), d1_ = sv[k].z * (1.0f / DM);
            mw[k] = pack2(__uint_as_float(pw << 16) + d0_, __uint_as_float(pw & 0xffff0000u) + d1_);
            const uint32_t vr = pack2(fmaxf(fmaf(-d0_, d0_, sv[k].y * (1.0f / DM)), 0.f), fmaxf(fmaf(-d1_, d1_, sv[k].w * (1.0f / DM)), 0.f));
            const uint32_t ve = pack2(__uint_as_float(vr << 16) + 1e-5f, __uint_as_float(vr & 0xffff0000u) + 1e-5f);
            const uint32_t sd = pack2(sqrt_apx(__uint_as_float(ve << 16)), sqrt_apx(__uint_as_float(ve & 0xffff0000u)));
            rs[2 * k] = rcp_apx(__uint_as_float(sd << 16)); rs[2 * k + 1] = rcp_apx(__uint_as_float(sd & 0xffff0000u));
        }
        if (rs[0] != 123.f) TSTAMP(13);
        const int ch = tid + UPADF / 8, pch = ch ^ ((ch >> 3) & 1);
#pragma unroll
        for (int c = 0; c < CV_CPB; c++) {
            *reinterpret_cast<uint4*>(Xs + c * XLEN + tid * 8) = xv[c];
            *reinterpret_cast<uint4*>(Us + c * ULEN + pch * 8) =
                make_uint4(ln2(xv[c].x, mw[0], rs[0], rs[1]), ln2(xv[c].y, mw[1], rs[2], rs[3]), ln2(xv[c].z, mw[2], rs[4], rs[5]), ln2(xv[c].w, mw[3], rs[6], rs[7]));
        }
    }
    __syncthreads();
    TSTAMP(1);
#pragma unroll 1
    for (int rd = rd0; rd < (int)rd1; rd++) {
        const int i = 32 * rd + lane;
        if (i < CV_CPB * 193) {
            const int c = i / 193, chunk = i - c * 193 - 1, ch = chunk + UPADF / 8;
            const bf16* uc = Us + c * ULEN;
            const uint4 o = *reinterpret_cast<const uint4*>(uc + (ch ^ ((ch >> 3) & 1)) * 8);
            const uint2 lo = *reinterpret_cast<const uint2*>(uc + ((ch - 1) ^ (((ch - 1) >> 3) & 1)) * 8 + 4);
            const uint2 hi = *reinterpret_cast<const uint2*>(uc + ((ch + 1) ^ (((ch + 1) >> 3) & 1)) * 8);
            const uint32_t w[8] = {lo.x, lo.y, o.x, o.y, o.z, o.w, hi.x, hi.y};
            float v[16], b[8];
#pragma unroll
            for (int k = 0; k < 8; k++) { v[2 * k] = __uint_as_float(w[k] << 16); v[2 * k + 1] = __uint_as_float(w[k] & 0xffff0000u); }
            unsigned char* bx = sm + CV_SM_B + c * BX_LEN + chunk * 16;
#pragma unroll
            for (int k = 0; k < 8; k++) b[k] = v[k + 4] + (v[k + 3] + v[k + 5]);
            *reinterpret_cast<uint2*>(bx + BX_3 + 168) = make_uint2(pack2(b[0], b[1]), pack2(b[2], b[3]));
            *reinterpret_cast<uint2*>(bx + BX_3 + 176) = make_uint2(pack2(b[4], b[5]), pack2(b[6], b[7]));
#pragma unroll
            for (int k = 0; k < 8; k++) b[k] += v[k + 2] + v[k + 6];
            *reinterpret_cast<uint4*>(bx + BX_5 + 160) = make_uint4(pack2(b[0], b[1]), pack2(b[2], b[3]), pack2(b[4], b[5]), pack2(b[6], b[7]));
            if (chunk < 128) {
#pragma unroll
                for (int k = 0; k < 8; k++) b[k] += v[k + 1] + v[k + 7];
                *reinterpret_cast<uint4*>(bx + BX_7 + 272) = make_uint4(pack2(b[0], b[1]), pack2(b[2], b[3]), pack2(b[4], b[5]), pack2(b[6], b[7]));
#pragma unroll
                for (int k = 0; k < 8; k++) b[k] += v[k] + v[k + 8];
                *reinterpret_cast<uint4*>(bx + BX_9 + 272) = make_uint4(pack2(b[0], b[1]), pack2(b[2], b[3]), pack2(b[4], b[5]), pack2(b[6], b[7]));
            }
        }
    }
    __syncwarp();
    if (lane == 0) mbar_arrive(smem_u32(sm + CV_SM_CNT) + 96);
    TSTAMP(2);
    {
        float acc[8][4];
#pragma unroll
        for (int j = 0; j < 8; j++)
#pragma unroll
            for (int k = 0; k < 4; k++) acc[j][k] = 0.f;
#pragma unroll 1
        for (int pass = (type == 2 || type == 4) ? 1 : 0; pass < ((type == 1 || type == 3) ? 1 : 2); pass++) {
            const uint32_t o0 = pass ? lds_off[2] : lds_off[0], o1 = pass ? lds_off[3] : lds_off[1];
            if (H) direct_pass<true>(acc, ubase + T0 * 256, o0, o1, Tc + 64 * pass, pass == 0);
            else direct_pass<false>(acc, ubase, o0, o1, Tc + 64 * pass, pass == 0);
        }
        TSTAMP(6);
        mbar_wait(smem_u32(sm + CV_SM_CNT) + 96, 0);
        if (type != 1 && type != 4) {
            const uint32_t* w2 = reinterpret_cast<const uint32_t*>(sm + CV_SM_T + c * TAPB + TAP_W2) + (115 - 96) + 4 * g - 2 * ti;
            uint32_t f[10][2];
#pragma unroll
            for (int k = 0; k < 10; k++) { f[k][0] = w2[16 * k]; f[k][1] = w2[16 * k - 8]; }
            const uint32_t ab = bbase + off2 + (2 * T0 + 6) * 128;
            const int kmax = H ? 23 : 8;
            uint32_t a[3][4];
            ldsm_x4_t(a[0], ab);
            ldsm_x4_t(a[1], ab - 128);
#pragma unroll
            for (int kp = 0; kp < 24; kp++) {
                if (kp > kmax) break;
                if (kp < 22) ldsm_x4_t(a[(kp + 2) % 3], ab - min(kp + 2, kmax) * 128);
#pragma unroll
                for (int j = 0; j < 8; j++) {
                    const int ee = 2 * j - 14 + kp;
                    if (ee >= 0 && ee <= 9) mma_bf16(acc[j], a[kp % 3][0], a[kp % 3][1], a[kp % 3][2], a[kp % 3][3], f[ee][0], f[ee][1]);
                }
            }
        }
        TSTAMP(7);
        if (type != 2 && type != 4) {
            const uint32_t* w3 = reinterpret_cast<const uint32_t*>(sm + CV_SM_T + c * TAPB + TAP_W3) + (129 - 96) + 2 * (g - ti);
            uint32_t f[9][2];
#pragma unroll
            for (int k = 0; k < 9; k++) { f[k][0] = w3[16 * k]; f[k][1] = w3[16 * k - 8]; }
            const uint32_t ab = bbase + off3 + (T0 - 2) * 256;
            uint32_t a[3][4];
            ldsm_x4_t(a[0], ab);
            ldsm_x4_t(a[1], ab - H * 256);
#pragma unroll
            for (int kp = 0; kp < 9; kp++) {
                if (kp > T0) break;
                if (kp < 7) ldsm_x4_t(a[(kp + 2) % 3], ab - min(kp + 2, T0) * 256);
#pragma unroll
                for (int j = 0; j < 8; j++) {
                    const int dl = j - 7 + kp;
                    if (dl >= 0 && dl <= 8) mma_bf16(acc[j], a[kp % 3][0], a[kp % 3][1], a[kp % 3][2], a[kp % 3][3], f[dl][0], f[dl][1]);
                }
            }
            const uint2* Dc = reinterpret_cast<const uint2*>(sm + CV_SM_T + c * TAPB + TAP_C) + e;
            const uint2 h63 = Dc[16], h64 = Dc[32], l63 = Dc[8], l64 = Dc[24];
#pragma unroll
            for (int j = 0; j < 8; j++)
                if (j == 7 || H) {
                    uint32_t bq[4];
                    ldsm_x4(bq, ubase + offc + (T0 + j - 8) * 256);
                    mma_bf16(acc[j], h64.x, h64.y, l64.x, l64.y, bq[0], bq[1]);
                    mma_bf16(acc[j], h63.x, h63.y, l63.x, l63.y, bq[2], bq[3]);
                }
        }
        TSTAMP(8);
        const bool hi_half = (type == 2 || type == 4);
        if (type != 0) {
            const int pair = H ? c : 5;
            float4* give = reinterpret_cast<float4*>(sm + CV_SM_P + pair * 4096 + (hi_half ? 2048 : 0)) + lane;
            const float4* take = reinterpret_cast<const float4*>(sm + CV_SM_P + pair * 4096 + (hi_half ? 0 : 2048)) + lane;
            const uint32_t pb = smem_u32(sm + CV_SM_CNT) + pair * 16;
#pragma unroll
            for (int j = 0; j < 4; j++)
                give[32 * j] = hi_half ? make_float4(acc[j][0], acc[j][1], acc[j][2], acc[j][3]) : make_float4(acc[j + 4][0], acc[j + 4][1], acc[j + 4][2], acc[j + 4][3]);
            __syncwarp();
            if (lane == 0) mbar_arrive(pb + (hi_half ? 8 : 0));
            mbar_wait(pb + (hi_half ? 0 : 8), 0);
#pragma unroll
            for (int j = 0; j < 4; j++) {
                const float4 v = take[32 * j];
                acc[j][0] = (hi_half ? acc[j + 4][0] : acc[j][0]) + v.x; acc[j][1] = (hi_half ? acc[j + 4][1] : acc[j][1]) + v.y;
                acc[j][2] = (hi_half ? acc[j + 4][2] : acc[j][2]) + v.z; acc[j][3] = (hi_half ? acc[j + 4][3] : acc[j][3]) + v.w;
            }
        }
        const uint32_t dk = __shfl_sync(~0u, (uint32_t)dskr, c) * 0x10001u;
#pragma unroll 1
        for (int rnd = 0; rnd < (type == 0 ? 2 : 1); rnd++) {
            const int Q = 2 * H + (hi_half ? 1 : rnd);
            if (rnd) {
#pragma unroll
                for (int j = 0; j < 4; j++)
#pragma unroll
                    for (int k = 0; k < 4; k++) acc[j][k] = acc[j + 4][k];
            }
            const uint32_t ya = smem_u32(Ys + c * XLEN) + (128 * (4 * Q + (lane >> 4)) + 16 * (lane & 7) + 8 * ((lane >> 3) & 1)) * 2;
#pragma unroll
            for (int j = 0; j < 4; j += 2)
                asm volatile("stmatrix.sync.aligned.m8n8.x4.trans.shared.b16 [%0], {%1,%2,%3,%4};" ::"r"(ya + j * 256),
                             "r"(pack2(acc[j][0], acc[j][1])), "r"(pack2(acc[j][2], acc[j][3])),
                             "r"(pack2(acc[j + 1][0], acc[j + 1][1])), "r"(pack2(acc[j + 1][2], acc[j + 1][3])) : "memory");
            __syncwarp();
            uint4 yv[2], xv[2], uv[2];
#pragma unroll
            for (int k = 0; k < 2; k++) {
                const int t = 512 * Q + 256 * k + 8 * lane, cu = (t + UPADF) >> 3;
                yv[k] = *reinterpret_cast<const uint4*>(Ys + c * XLEN + t);
                xv[k] = *reinterpret_cast<const uint4*>(Xs + c * XLEN + t);
                uv[k] = *reinterpret_cast<const uint4*>(Us + c * ULEN + (cu ^ ((cu >> 3) & 1)) * 8);
            }
#pragma unroll
            for (int k = 0; k < 2; k++)
                asm volatile("st.relaxed.gpu.global.v4.u32 [%0], {%1,%2,%3,%4};" ::"l"((layer ? g_yT : g_xcT) + (size_t)(d0 + c) * XCP + 512 * Q + 256 * k + 8 * lane),
                             "r"(fin2(xv[k].x, yv[k].x, uv[k].x, dk)), "r"(fin2(xv[k].y, yv[k].y, uv[k].y, dk)), "r"(fin2(xv[k].z, yv[k].z, uv[k].z, dk)), "r"(fin2(xv[k].w, yv[k].w, uv[k].w, dk)) : "memory");
        }
        TSTAMP(4);
        if (layer == 1) {
            const int mb = blockIdx.x >> 3, cg = blockIdx.x & 7;
            const bf16* src = g_yT + (size_t)(cg * 80 + (tid >> 4)) * XCP + mb * 128 + (tid & 15) * 8;
            uint32_t v[3][4];
            __syncthreads();
            TSTAMP(5);
            uint32_t todo = warp < 8 ? 7 : 3;
#pragma unroll 1
            for (int it = 0; it < SPIN_MAX; it++) {
#pragma unroll
                for (int k = 0; k < 3; k++)
                    if (todo >> k & 1)
                        asm volatile("ld.relaxed.gpu.global.v4.u32 {%0,%1,%2,%3}, [%4];" : "=r"(v[k][0]), "=r"(v[k][1]), "=r"(v[k][2]), "=r"(v[k][3]) : "l"(src + k * (32 * XCP)) : "memory");
#pragma unroll
                for (int k = 0; k < 3; k++)
                    if ((todo >> k & 1) && v[k][0] != ~0u && v[k][1] != ~0u && v[k][2] != ~0u && v[k][3] != ~0u) {
                        *reinterpret_cast<uint4*>(sm + (32 * k + (tid >> 4)) * 272 + (tid & 15) * 16) = make_uint4(v[k][0], v[k][1], v[k][2], v[k][3]);
                        todo ^= 1u << k;
                    }
                if (!todo) break;
                __nanosleep(CV_SLEEP);
            }
            __syncthreads();
            uint32_t w[12];
#pragma unroll
            for (int k = 0; k < 3; k++) ldsm_x4(&w[4 * k], smem_u32(sm) + min(32 * k + lane, 79) * 272 + warp * 16);
            const uint32_t ot = smem_u32(sm + CV_SM_O) + warp * 1280, oa = ot + (lane & 7) * 160 + (lane >> 3) * 16;
            stsm_x4_t(oa, w[0], w[1], w[2], w[3]);
            stsm_x4_t(oa + 64, w[4], w[5], w[6], w[7]);
            asm volatile("stmatrix.sync.aligned.m8n8.x2.trans.shared.b16 [%0], {%1,%2};" ::"r"(oa + 128), "r"(w[8]), "r"(w[9]) : "memory");
            fence_async_smem();
            __syncwarp();
            if (lane == 0) tma_store_2d(&tmOut, cg * 80, mb * 128 + 8 * warp, ot);
        }
    }
    TSTAMP(3);
    GSTAMP(g_tim, 14);
    SPAN(3 + 4 * layer, 3);
}

__device__ __forceinline__ void wgmma_fence() { asm volatile("wgmma.fence.sync.aligned;" ::: "memory"); }
__device__ __forceinline__ void wgmma_commit() { asm volatile("wgmma.commit_group.sync.aligned;" ::: "memory"); }
template <int N> __device__ __forceinline__ void wgmma_wait() { asm volatile("wgmma.wait_group.sync.aligned %0;" ::"n"(N) : "memory"); }
__device__ __forceinline__ uint64_t make_desc(uint32_t addr, uint32_t lbo, uint32_t sbo, uint32_t mode) {
    return (uint64_t)((addr & 0x3FFFF) >> 4) | ((uint64_t)(lbo >> 4) << 16) | ((uint64_t)(sbo >> 4) << 32) | ((uint64_t)mode << 62);
}
template <int TA, int TB>
__device__ __forceinline__ void wgmma_n240(float (&d)[120], uint64_t da, uint64_t db) {
    asm volatile("wgmma.mma_async.sync.aligned.m64n240k16.f32.bf16.bf16 {%0,%1,%2,%3,%4,%5,%6,%7,%8,%9,%10,%11,%12,%13,%14,%15,%16,%17,%18,%19,%20,%21,%22,%23,%24,%25,%26,%27,%28,%29,%30,%31,%32,%33,%34,%35,%36,%37,%38,%39,%40,%41,%42,%43,%44,%45,%46,%47,%48,%49,%50,%51,%52,%53,%54,%55,%56,%57,%58,%59,%60,%61,%62,%63,%64,%65,%66,%67,%68,%69,%70,%71,%72,%73,%74,%75,%76,%77,%78,%79,%80,%81,%82,%83,%84,%85,%86,%87,%88,%89,%90,%91,%92,%93,%94,%95,%96,%97,%98,%99,%100,%101,%102,%103,%104,%105,%106,%107,%108,%109,%110,%111,%112,%113,%114,%115,%116,%117,%118,%119}, %120, %121, 1, 1, 1, %122, %123;"
                 : "+f"(d[0]), "+f"(d[1]), "+f"(d[2]), "+f"(d[3]), "+f"(d[4]), "+f"(d[5]), "+f"(d[6]), "+f"(d[7]), "+f"(d[8]), "+f"(d[9]), "+f"(d[10]), "+f"(d[11]), "+f"(d[12]), "+f"(d[13]), "+f"(d[14]), "+f"(d[15]), "+f"(d[16]), "+f"(d[17]), "+f"(d[18]), "+f"(d[19]), "+f"(d[20]), "+f"(d[21]), "+f"(d[22]), "+f"(d[23]), "+f"(d[24]), "+f"(d[25]), "+f"(d[26]), "+f"(d[27]), "+f"(d[28]), "+f"(d[29]), "+f"(d[30]), "+f"(d[31]), "+f"(d[32]), "+f"(d[33]), "+f"(d[34]), "+f"(d[35]), "+f"(d[36]), "+f"(d[37]), "+f"(d[38]), "+f"(d[39]), "+f"(d[40]), "+f"(d[41]), "+f"(d[42]), "+f"(d[43]), "+f"(d[44]), "+f"(d[45]), "+f"(d[46]), "+f"(d[47]), "+f"(d[48]), "+f"(d[49]), "+f"(d[50]), "+f"(d[51]), "+f"(d[52]), "+f"(d[53]), "+f"(d[54]), "+f"(d[55]), "+f"(d[56]), "+f"(d[57]), "+f"(d[58]), "+f"(d[59]), "+f"(d[60]), "+f"(d[61]), "+f"(d[62]), "+f"(d[63]), "+f"(d[64]), "+f"(d[65]), "+f"(d[66]), "+f"(d[67]), "+f"(d[68]), "+f"(d[69]), "+f"(d[70]), "+f"(d[71]), "+f"(d[72]), "+f"(d[73]), "+f"(d[74]), "+f"(d[75]), "+f"(d[76]), "+f"(d[77]), "+f"(d[78]), "+f"(d[79]), "+f"(d[80]), "+f"(d[81]), "+f"(d[82]), "+f"(d[83]), "+f"(d[84]), "+f"(d[85]), "+f"(d[86]), "+f"(d[87]), "+f"(d[88]), "+f"(d[89]), "+f"(d[90]), "+f"(d[91]), "+f"(d[92]), "+f"(d[93]), "+f"(d[94]), "+f"(d[95]), "+f"(d[96]), "+f"(d[97]), "+f"(d[98]), "+f"(d[99]), "+f"(d[100]), "+f"(d[101]), "+f"(d[102]), "+f"(d[103]), "+f"(d[104]), "+f"(d[105]), "+f"(d[106]), "+f"(d[107]), "+f"(d[108]), "+f"(d[109]), "+f"(d[110]), "+f"(d[111]), "+f"(d[112]), "+f"(d[113]), "+f"(d[114]), "+f"(d[115]), "+f"(d[116]), "+f"(d[117]), "+f"(d[118]), "+f"(d[119])
                 : "l"(da), "l"(db), "n"(TA), "n"(TB));
}

template <int TA, int TB>
__device__ __forceinline__ void wgmma_n80(float (&d)[40], uint64_t da, uint64_t db) {
    asm volatile("wgmma.mma_async.sync.aligned.m64n80k16.f32.bf16.bf16 {%0,%1,%2,%3,%4,%5,%6,%7,%8,%9,%10,%11,%12,%13,%14,%15,%16,%17,%18,%19,%20,%21,%22,%23,%24,%25,%26,%27,%28,%29,%30,%31,%32,%33,%34,%35,%36,%37,%38,%39}, %40, %41, 1, 1, 1, %42, %43;"
                 : "+f"(d[0]), "+f"(d[1]), "+f"(d[2]), "+f"(d[3]), "+f"(d[4]), "+f"(d[5]), "+f"(d[6]), "+f"(d[7]), "+f"(d[8]), "+f"(d[9]), "+f"(d[10]), "+f"(d[11]), "+f"(d[12]), "+f"(d[13]), "+f"(d[14]), "+f"(d[15]), "+f"(d[16]), "+f"(d[17]), "+f"(d[18]), "+f"(d[19]), "+f"(d[20]), "+f"(d[21]), "+f"(d[22]), "+f"(d[23]), "+f"(d[24]), "+f"(d[25]), "+f"(d[26]), "+f"(d[27]), "+f"(d[28]), "+f"(d[29]), "+f"(d[30]), "+f"(d[31]), "+f"(d[32]), "+f"(d[33]), "+f"(d[34]), "+f"(d[35]), "+f"(d[36]), "+f"(d[37]), "+f"(d[38]), "+f"(d[39])
                 : "l"(da), "l"(db), "n"(TA), "n"(TB));
}

constexpr int A1_THREADS = 384;
constexpr int A1_NST = 4;
#define A1_PRE0 2
#define A1_SDELAY 1
#define A1_SKEW 8
#define A1_PRE1 1
constexpr int A1_STAGE = 16384 + WQ_STAGE;
constexpr int A1_KVP = 336;
constexpr int A1_SM_KV = 2 * A1_STAGE;
constexpr int A1_SM_O = A1_SM_KV + 144 * A1_KVP;
constexpr int A1_SM_R = A1_NST * A1_STAGE;
constexpr int A1_SM_BAR = A1_SM_R + 20480;
constexpr int A1_SM_CS = A1_SM_BAR + 256;
constexpr int A1_SM_RS = A1_SM_CS + 1024;
constexpr int A1_SMEM = A1_SM_RS + 1024 + 1024;
static_assert(A1_SM_O % 128 == 0 && A1_SM_O + 20480 <= A1_SM_R, "layout");

template <int L>
__device__ __forceinline__ void a1_mainloop(float (&acc)[120], uint32_t sbase, uint32_t bars, int wg, int tile) {
    constexpr int layer = L; (void)layer;
    const uint64_t da0 = L ? make_desc(sbase + wg * 8192, 8192, 1024, 1) : make_desc(sbase + wg * 8192, 16, 1024, 1), db0 = make_desc(sbase + 16384, 16, 1024, 1);
#pragma unroll 1
    for (int t = 0; t < 10; t++) {
        const int st = t % A1_NST;
        mbar_wait(bars + 8 * st, (t / A1_NST) & 1);
        if (t == A1_SKEW && wg == 0) mbar_wait(bars + 160, 0);
        TSTAMP3(1 + t);
        wgmma_fence();
#pragma unroll
        for (int kk = 0; kk < 4; kk++) wgmma_n240<L, 0>(acc, da0 + (uint32_t)(st * (A1_STAGE / 16) + kk * (L ? 128 : 2)), db0 + (uint32_t)(st * (A1_STAGE / 16) + kk * 2));
        wgmma_commit();
        if (t == 9 && threadIdx.x == 128) { mbar_arrive(bars + 160); mbar_arrive(bars + 144); }
        if (t == A1_SKEW - 1 && wg == 0) wgmma_wait<0>(); else wgmma_wait<1>();
        if (t > 0 && t < 9 && (threadIdx.x & 127) == 0) {
            if (t != A1_SKEW || wg) mbar_arrive(bars + 8 * (A1_NST + (t - 1) % A1_NST));
            if (t == A1_SKEW - 1 && wg == 0) mbar_arrive(bars + 8 * (A1_NST + t % A1_NST));
        }
    }
}

__global__ void __launch_bounds__(A1_THREADS, 1) a1_kernel(const int layer, const bf16* __restrict__ x0, const __grid_constant__ CUtensorMap tmX,
                                                           const __grid_constant__ CUtensorMap tmR, const __grid_constant__ CUtensorMap tmOst) {
    extern __shared__ unsigned char smraw[];
    const uint32_t sbase = (smem_u32(smraw) + 1023) & ~1023u;
    const uint32_t bars = sbase + A1_SM_BAR;
    const uint32_t bar_stat = bars + 64, bar_kv = bars + 72, bar_r = bars + 152;
    const int tid = threadIdx.x, w = __shfl_sync(~0u, tid >> 5, 0), wg = w >> 2;
    const int tile = sm_tile();
    if (tile >= 128) { sm_idle(2 * layer); return; }
    const int mb = (tile >> 2) & 15, hg = 4 * (tile >> 6) + (tile & 3);
    unsigned char* stg = smraw + (sbase - smem_u32(smraw));
    float* cs = reinterpret_cast<float*>(stg + A1_SM_CS);
    float2* rst = reinterpret_cast<float2*>(stg + A1_SM_RS);
    const int pre = layer ? A1_PRE1 : A1_PRE0;
    auto issue_w = [&](int kb) {
        bulk_load(sbase + (kb % A1_NST) * A1_STAGE + 16384, reinterpret_cast<const unsigned char*>(g_wq) + (hg * 10 + kb) * WQ_STAGE, WQ_STAGE, bars + 8 * (kb % A1_NST));
    };
    auto issue_x = [&](int kb) {
        const uint32_t dst = sbase + (kb % A1_NST) * A1_STAGE, full = bars + 8 * (kb % A1_NST);
        if (layer == 0) tma_load_2d(dst, &tmX, kb * 64, mb * 128, full);
        else { tma_load_2d(dst, &tmX, mb * 128, kb * 64, full); tma_load_2d(dst + 8192, &tmX, mb * 128 + 64, kb * 64, full); }
    };
    if (w == 8) {
        if (tid == 256) {
            prefetch_tmap(&tmX);
#pragma unroll
            for (int i = 0; i < A1_NST; i++) { mbar_init(bars + 8 * i, 1); mbar_init(bars + 8 * (A1_NST + i), 2); }
            mbar_init(bar_r, 1);
            asm volatile("fence.mbarrier_init.release.cluster;" ::: "memory");
#pragma unroll
            for (int i = 0; i < A1_NST; i++) mbar_expect_tx(bars + 8 * i, A1_STAGE);
            mbar_expect_tx(bar_r, 20480);
        }
        __syncwarp();
        asm volatile("bar.arrive 0, 384;" ::: "memory");
        if (tid == 256) {
#pragma unroll 1
            for (int kb = 0; kb < pre; kb++) { if (layer) issue_w(kb); else issue_x(kb); }
            pdl_sync();
#pragma unroll 1
            for (int kb = 0; kb < A1_NST; kb++) {
                if (kb == A1_SDELAY && layer) {
                    tma_load_2d(sbase + A1_SM_R, &tmR, mb * 128, hg * 80, bar_r); tma_load_2d(sbase + A1_SM_R + 10240, &tmR, mb * 128 + 64, hg * 80, bar_r);
                }
                if (kb >= pre || layer) issue_x(kb);
                if (kb >= pre || !layer) issue_w(kb);
            }
        }
    } else {
        if (tid == 0) {
            mbar_init(bar_stat, 2);
#pragma unroll
            for (int i = 0; i < 9; i++) mbar_init(bar_kv + 8 * i, i ? 1 : 4);
            mbar_init(bars + 144, 1);
            mbar_init(bars + 160, 1);
            asm volatile("fence.mbarrier_init.release.cluster;" ::: "memory");
        } else if (tid == 320) { prefetch_tmap(&tmR); prefetch_tmap(&tmOst); }
        asm volatile("bar.sync 0, 384;" ::: "memory");
    }
    SPAN(1 + 4 * layer, 0);
    const uint32_t tag = ld_epoch();
    if (tid == 352) sm_started(2 * layer);
    constexpr int on = 1;
    if (wg == 2) {
        if (w == 9) {
        } else if (w == 8) {
            if (tid == 256) {
#pragma unroll 1
                for (int kb = A1_NST; kb < 10; kb++) {
                    mbar_wait(bars + 8 * (A1_NST + kb % A1_NST), ((kb / A1_NST) - 1) & 1);
                    mbar_expect_tx(bars + 8 * (kb % A1_NST), A1_STAGE);
                    issue_x(kb); issue_w(kb);
                }
                TSTAMP1T(6, 256);
            }
            __syncwarp();
        } else {
            const int j = tid - 320;
            if (layer == 0) {
                const uint4* src = reinterpret_cast<const uint4*>(x0 + (size_t)(mb * 128 + hg * 16 + (j >> 2)) * DM);
                uint4 v[20];
#pragma unroll
                for (int k = 0; k < 20; k++) v[k] = __ldg(src + (j & 3) + 4 * k);
                const float p0 = __uint_as_float(__shfl_sync(~0u, v[0].x, j & 28) << 16);
                float s[2] = {0.f, 0.f}, q[2] = {0.f, 0.f};
#pragma unroll
                for (int k = 0; k < 20; k++) {
                    const uint32_t w[4] = {v[k].x, v[k].y, v[k].z, v[k].w};
#pragma unroll
                    for (int i = 0; i < 4; i++) {
                        const float a = __uint_as_float(w[i] << 16) - p0, b = __uint_as_float(w[i] & 0xffff0000u) - p0;
                        s[0] += a; s[1] += b; q[0] = fmaf(a, a, q[0]); q[1] = fmaf(b, b, q[1]);
                    }
                }
                float s0 = s[0] + s[1], q0 = q[0] + q[1];
#pragma unroll
                for (int o = 1; o <= 2; o <<= 1) { s0 += __shfl_xor_sync(~0u, s0, o); q0 += __shfl_xor_sync(~0u, q0, o); }
                if ((j & 3) == 0) {
                    const float d = s0 * (1.0f / DM);
                    const uint32_t ms = pack2(p0 + d, sqrt_apx(rbf(rbf(fmaxf(fmaf(-d, d, q0 * (1.0f / DM)), 0.f)) + 1e-5f)));
                    asm volatile("st.global.cg.u64 [%0], %1;" ::"l"(g_rstat + mb * 128 + hg * 16 + (j >> 2)), "l"(tagw(ms, tag)) : "memory");
                    g_piv[mb * 128 + hg * 16 + (j >> 2)] = __ushort_as_bfloat16((unsigned short)ms);
                }
                pdl_sync();
            }
            if (j < 60) {
                float4 a = make_float4(0.f, 0.f, 0.f, 0.f);
#pragma unroll
                for (int k = 0; k < 10; k++) {
                    const float4 v = __ldcg(reinterpret_cast<const float4*>(g_csp + k * 1920 + hg * 240) + j);
                    a.x += v.x; a.y += v.y; a.z += v.z; a.w += v.w;
                }
                reinterpret_cast<float4*>(cs)[j] = a;
            }
            if (layer == 0) {
                ulonglong2 v;
#pragma unroll 1
                for (int it = 0; it < SPIN_MAX; it++) {
                    v = ld_tag2(reinterpret_cast<const ulonglong2*>(g_rstat + mb * 128) + j);
                    if (tag_ok(v, tag)) break;
                    __nanosleep(100);
                }
                *reinterpret_cast<float4*>(rst + 2 * j) = make_float4(__uint_as_float((uint32_t)v.x << 16), rcp_apx(__uint_as_float((uint32_t)v.x & 0xffff0000u)),
                                                                      __uint_as_float((uint32_t)v.y << 16), rcp_apx(__uint_as_float((uint32_t)v.y & 0xffff0000u)));
            } else {
                const int ch = j & 7, kg = (j >> 3) & 3;
                const unsigned char* src = stg + A1_SM_R + (j >> 5) * 10240;
                mbar_wait(bar_r, 0);
                uint4 v[20];
#pragma unroll
                for (int k = 0; k < 20; k++) v[k] = *reinterpret_cast<const uint4*>(src + (4 * k + kg) * 128 + ((ch ^ ((4 * k + kg) & 7)) << 4));
                const uint4 pv = *reinterpret_cast<const uint4*>(src + (ch << 4));
                float s[8], q[8], p0[8] = {__uint_as_float(pv.x << 16), __uint_as_float(pv.x & 0xffff0000u), __uint_as_float(pv.y << 16), __uint_as_float(pv.y & 0xffff0000u),
                                           __uint_as_float(pv.z << 16), __uint_as_float(pv.z & 0xffff0000u), __uint_as_float(pv.w << 16), __uint_as_float(pv.w & 0xffff0000u)};
#pragma unroll
                for (int i = 0; i < 8; i++) { s[i] = 0.f; q[i] = 0.f; }
#pragma unroll
                for (int k = 0; k < 20; k++) {
                    const uint32_t w[4] = {v[k].x, v[k].y, v[k].z, v[k].w};
#pragma unroll
                    for (int i = 0; i < 4; i++) {
                        const float a = __uint_as_float(w[i] << 16) - p0[2 * i], b = __uint_as_float(w[i] & 0xffff0000u) - p0[2 * i + 1];
                        s[2 * i] += a; s[2 * i + 1] += b; q[2 * i] = fmaf(a, a, q[2 * i]); q[2 * i + 1] = fmaf(b, b, q[2 * i + 1]);
                    }
                }
#pragma unroll
                for (int i = 0; i < 4; i++) {
                    const bool up = kg & 2;
                    const float ss = __shfl_xor_sync(~0u, up ? s[i] : s[i + 4], 16), qq = __shfl_xor_sync(~0u, up ? q[i] : q[i + 4], 16);
                    s[i] = (up ? s[i + 4] : s[i]) + ss; q[i] = (up ? q[i + 4] : q[i]) + qq; p0[i] = up ? p0[i + 4] : p0[i];
                }
#pragma unroll
                for (int i = 0; i < 2; i++) {
                    const bool up = kg & 1;
                    const float ss = __shfl_xor_sync(~0u, up ? s[i] : s[i + 2], 8), qq = __shfl_xor_sync(~0u, up ? q[i] : q[i + 2], 8);
                    s[i] = (up ? s[i + 2] : s[i]) + ss; q[i] = (up ? q[i + 2] : q[i]) + qq; p0[i] = up ? p0[i + 2] : p0[i];
                }
#pragma unroll
                for (int r = 0; r < 2; r++) {
                    const float d = s[r] * (1.0f / 80.0f);
                    st_tag2(g_part + (mb * 8 + hg) * 128 + 64 * r + j, __float_as_uint(p0[r] + d), __float_as_uint(fmaxf(fmaf(-d, s[r], q[r]), 0.f)), tag);
                }
                const ulonglong2* gp = g_part + mb * 8 * 128 + j;
#pragma unroll 1
                for (int it = 0; it < SPIN_MAX; it++) {
                    if (__all_sync(~0u, tag_ok(ld_tag2(gp + (j & 7) * 128 + 64), tag))) break;
                    __nanosleep(200);
                }
                ulonglong2 pw[16];
#pragma unroll 1
                for (int it = 0; it < SPIN_MAX; it++) {
                    bool ok = true;
#pragma unroll
                    for (int k = 0; k < 16; k++) pw[k] = ld_tag2(gp + k * 64);
#pragma unroll
                    for (int k = 0; k < 16; k++) ok = ok && tag_ok(pw[k], tag);
                    if (ok) break;
                    __nanosleep(200);
                }
                float o[4];
#pragma unroll
                for (int r = 0; r < 2; r++) {
                    float mean = 0.f, m2 = 0.f;
#pragma unroll
                    for (int k = 0; k < 8; k++) mean += __uint_as_float((uint32_t)pw[2 * k + r].x);
                    mean *= 0.125f;
#pragma unroll
                    for (int k = 0; k < 8; k++) {
                        const float dm = __uint_as_float((uint32_t)pw[2 * k + r].x) - mean;
                        m2 += fmaf(80.0f * dm, dm, __uint_as_float((uint32_t)pw[2 * k + r].y));
                    }
                    o[2 * r] = rbf(mean);
                    o[2 * r + 1] = rcp_apx(rbf(sqrt_apx(rbf(rbf(m2 * (1.0f / DM)) + 1e-5f))));
                }
                const int row = (j >> 5) * 64 + (j & 7) * 8 + ((j >> 3) & 3) * 2;
                *reinterpret_cast<float4*>(rst + row) = make_float4(o[0], o[1], o[2], o[3]);
                if (hg == 0) *reinterpret_cast<uint32_t*>(g_piv + SEQ + mb * 128 + row) = __byte_perm(__float_as_uint(o[0]), __float_as_uint(o[2]), 0x7632);
            }
            TSTAMP1T(7, 320);
            __syncwarp();
            if ((tid & 31) == 0) mbar_arrive(bar_stat);
        }
    } else {
        float acc[120];
#pragma unroll
        for (int i = 0; i < 120; i++) acc[i] = 0.f;
        const int lane = tid & 31, warp = w & 7, g = lane >> 2, t = lane & 3;
        if (on) {
            pdl_sync();
            SPAN(1 + 4 * layer, 1);
            TSTAMP1(0);
            if (threadIdx.x == 0) { GSTAMP(g_tim1, 15); }
            TSTAMP3(0);
            if (layer == 0) a1_mainloop<0>(acc, sbase, bars, wg, tile); else a1_mainloop<1>(acc, sbase, bars, wg, tile);
            mbar_wait(bar_stat, 0);
            mbar_wait(bars + 8 * (A1_NST + 3), 1);
            wgmma_wait<0>();
        }
        const float2 sa_ = rst[16 * warp + g], sb_ = rst[16 * warp + g + 8];
        TSTAMP1(2);
        TSTAMP1T(13, 224);
        uint32_t f[30][2];
        auto norm = [&](int j0) {
            float2 cc[10];
#pragma unroll
            for (int j = 0; j < 10; j++) cc[j] = *reinterpret_cast<const float2*>(cs + 8 * (j0 + j) + 2 * t);
#pragma unroll
            for (int j = 0; j < 10; j++) {
                const float* a = acc + 4 * (j0 + j);
                f[j0 + j][0] = pack2(fmaf(-sa_.x, cc[j].x, a[0]) * sa_.y, fmaf(-sa_.x, cc[j].y, a[1]) * sa_.y);
                f[j0 + j][1] = pack2(fmaf(-sb_.x, cc[j].x, a[2]) * sb_.y, fmaf(-sb_.x, cc[j].y, a[3]) * sb_.y);
            }
        };
        norm(10); norm(20);
        if (warp == 7) {
            uint4* hout = g_halo + ((layer * 16 + mb) * 8 + hg) * 320 + lane;
#pragma unroll
            for (int j = 0; j < 20; j += 2)
                asm volatile("st.relaxed.gpu.global.v4.u32 [%0], {%1,%2,%3,%4};" ::"l"(hout + 16 * j), "r"(f[10 + j][0]), "r"(f[10 + j][1]), "r"(f[11 + j][0]), "r"(f[11 + j][1]) : "memory");
        }
        TSTAMP1T(12, 224);
        const uint32_t kvw = sbase + A1_SM_KV + 16 * warp * A1_KVP;
        const uint32_t mrow = kvw + (lane & 15) * A1_KVP + (lane >> 4) * 16;
#pragma unroll
        for (int j = 0; j < 20; j += 2) stsm_x4(mrow + 16 * A1_KVP + 16 * j, f[10 + j][0], f[10 + j][1], f[11 + j][0], f[11 + j][1]);
        __syncwarp();
        if (lane == 0 && on) mbar_arrive(bar_kv + 8 * (warp + 1));
        norm(0);
        TSTAMP1T(10, 64);
        float sc[4][4][4];
        uint32_t qs[4][2];
#pragma unroll
        for (int h = 0; h < 4; h++) {
            const int jb = 5 * (h >> 1) + 3 * (h & 1), js = 5 * (h >> 1) + 2;
            qs[h][0] = (t >> 1) == (h & 1) ? f[js][0] : 0u; qs[h][1] = (t >> 1) == (h & 1) ? f[js][1] : 0u;
#pragma unroll
            for (int nt = 2; nt < 4; nt++) {
#pragma unroll
                for (int e = 0; e < 4; e++) sc[h][nt][e] = 0.f;
                mma_bf16(sc[h][nt], f[jb][0], f[jb][1], f[jb + 1][0], f[jb + 1][1], f[10 + jb][nt - 2], f[11 + jb][nt - 2]);
                mma_bf16_k8(sc[h][nt], qs[h][0], qs[h][1], f[10 + js][nt - 2]);
            }
        }
        if (on) mbar_wait(bar_kv + 8 * warp, 0);
        TSTAMP1(8);
        uint32_t kp[10][2];
#pragma unroll
        for (int j = 0; j < 10; j += 2) ldsm_x4(&kp[j][0], mrow + 16 * j);
#pragma unroll
        for (int h = 0; h < 4; h++) {
            const int jb = 5 * (h >> 1) + 3 * (h & 1), js = 5 * (h >> 1) + 2;
#pragma unroll
            for (int nt = 0; nt < 2; nt++) {
#pragma unroll
                for (int e = 0; e < 4; e++) sc[h][nt][e] = 0.f;
                mma_bf16(sc[h][nt], f[jb][0], f[jb][1], f[jb + 1][0], f[jb + 1][1], kp[jb][nt], kp[jb + 1][nt]);
                mma_bf16_k8(sc[h][nt], qs[h][0], qs[h][1], kp[js][nt]);
            }
        }
        uint32_t vb[10][4];
#pragma unroll
        for (int j = 0; j < 10; j++) ldsm_x4_t(vb[j], kvw + lane * A1_KVP + 160 + 16 * j);
        TSTAMP1T(3, 64);
        const bool odd = g & 1, hi = t > (g >> 1), edge = (mb | warp) == 0;
        float p[4][4], mx[4][2], sum[4][2];
#pragma unroll
        for (int h = 0; h < 4; h++) {
#pragma unroll
            for (int r = 0; r < 2; r++) {
                const float a = odd ? sc[h][1 + r][2 * r + 1] : sc[h][1 + r][2 * r];
                const float b0 = odd ? sc[h][r][2 * r + 1] : sc[h][r][2 * r], b1 = odd ? sc[h][2 + r][2 * r + 1] : sc[h][2 + r][2 * r];
                const uint32_t w1 = pack2(a, hi ? b0 : b1);
                const uint32_t w2 = pack2(__uint_as_float(w1 << 16) * 0.22360679774997896f, __uint_as_float(w1 & 0xffff0000u) * 0.22360679774997896f);
                p[h][2 * r] = __uint_as_float(w2 << 16); p[h][2 * r + 1] = __uint_as_float(w2 & 0xffff0000u);
            }
            if (edge) {
                p[h][0] = -1.0e9f;
                if (hi) { p[h][1] = -1.0e9f; p[h][3] = -1.0e9f; }
            }
            mx[h][0] = fmaxf(p[h][0], p[h][1]); mx[h][1] = fmaxf(p[h][2], p[h][3]);
        }
#pragma unroll
        for (int o = 1; o <= 2; o <<= 1)
#pragma unroll
            for (int h = 0; h < 4; h++)
#pragma unroll
                for (int r = 0; r < 2; r++) mx[h][r] = fmaxf(mx[h][r], __shfl_xor_sync(~0u, mx[h][r], o));
#pragma unroll
        for (int h = 0; h < 4; h++)
#pragma unroll
            for (int r = 0; r < 2; r++) {
                p[h][2 * r] = __expf(p[h][2 * r] - mx[h][r]); p[h][2 * r + 1] = __expf(p[h][2 * r + 1] - mx[h][r]);
                sum[h][r] = p[h][2 * r] + p[h][2 * r + 1];
            }
#pragma unroll
        for (int o = 1; o <= 2; o <<= 1)
#pragma unroll
            for (int h = 0; h < 4; h++)
#pragma unroll
                for (int r = 0; r < 2; r++) sum[h][r] += __shfl_xor_sync(~0u, sum[h][r], o);
        TSTAMP1T(5, 64);
        const uint32_t selA = odd ? 0x1044u : 0x4410u, selB = odd ? 0x3244u : 0x4432u, selH = hi ? selB : 0x4444u, selL = hi ? 0x4444u : selB;
        const uint32_t orow = sbase + A1_SM_O + (16 * warp + (lane & 15)) * 160 + (lane >> 4) * 16;
        uint32_t ob[10][2];
#pragma unroll
        for (int P = 0; P < 2; P++) {
            float os[2][4];
#pragma unroll
            for (int e = 0; e < 2; e++) {
                const int h = 2 * P + e;
                const float i0 = rcp_apx(sum[h][0]), i1 = rcp_apx(sum[h][1]);
                const uint32_t w0 = pack2(p[h][0] * i0, p[h][1] * i0), w1 = pack2(p[h][2] * i1, p[h][3] * i1);
                const uint32_t a00 = __byte_perm(w0, 0, selH), a02 = __byte_perm(w0, 0, selA), a03 = __byte_perm(w1, 0, selH);
                const uint32_t a10 = __byte_perm(w0, 0, selL), a11 = __byte_perm(w1, 0, selA), a13 = __byte_perm(w1, 0, selL);
#pragma unroll
                for (int dt = 0; dt < 3; dt++) {
                    const int j = 5 * P + (dt < 2 ? 3 * e + dt : 2);
                    float o[4] = {0.f, 0.f, 0.f, 0.f};
                    mma_bf16(o, a00, 0u, a02, a03, vb[j][0], vb[j][1]);
                    mma_bf16(o, a10, a11, 0u, a13, vb[j][2], vb[j][3]);
                    if (dt < 2) { ob[j][0] = pack2(o[0], o[1]); ob[j][1] = pack2(o[2], o[3]); }
                    else { os[e][0] = o[0]; os[e][1] = o[1]; os[e][2] = o[2]; os[e][3] = o[3]; }
                }
            }
            ob[5 * P + 2][0] = t < 2 ? pack2(os[0][0], os[0][1]) : pack2(os[1][0], os[1][1]);
            ob[5 * P + 2][1] = t < 2 ? pack2(os[0][2], os[0][3]) : pack2(os[1][2], os[1][3]);
        }
#pragma unroll
        for (int j = 0; j < 10; j += 2) stsm_x4(orow + 16 * j, ob[j][0], ob[j][1], ob[j + 1][0], ob[j + 1][1]);
        fence_async_smem();
        __syncwarp();
        if (on) {
            if (lane == 0) tma_store_2d(&tmOst, hg * 80, mb * 128 + 16 * warp, sbase + A1_SM_O + 16 * warp * 160);
            TSTAMP1T(4, 64);
            TSTAMP1(1);
            GSTAMP(g_tim1, 14);
            SPAN(1 + 4 * layer, 3);
            return;
        }
    }
    mbar_wait(bars + 144, 0);
    mbar_wait(bars + 8 * (A1_NST + 3), 1);
    const uint4* hin = g_halo + ((layer * 16 + mb - 1) * 8 + hg) * 320 + tid - 256;
    uint32_t hv[3][4] = {};
    if (mb > 0) {
#pragma unroll 1
        for (int it = 0; it < SPIN_MAX; it++) {
            bool ok = true;
#pragma unroll
            for (int k = 0; k < 3; k++)
                if (k < 2 || w < 10)
                    asm volatile("ld.relaxed.gpu.global.v4.u32 {%0,%1,%2,%3}, [%4];" : "=r"(hv[k][0]), "=r"(hv[k][1]), "=r"(hv[k][2]), "=r"(hv[k][3]) : "l"(hin + 128 * k) : "memory");
#pragma unroll
            for (int k = 0; k < 3; k++) ok = ok && hv[k][0] != ~0u && hv[k][1] != ~0u && hv[k][2] != ~0u && hv[k][3] != ~0u;
            if (ok) break;
        }
    }
    __syncwarp();
    TSTAMP1T(11, 256);
    const uint32_t hd = sbase + A1_SM_KV + (tid & 15) * A1_KVP + ((tid >> 4) & 1) * 16 + (w - 8) * 32;
#pragma unroll
    for (int k = 0; k < 3; k++)
        if (k < 2 || w < 10) stsm_x4(hd + 128 * k, hv[k][0], hv[k][1], hv[k][2], hv[k][3]);
    __syncwarp();
    if ((tid & 31) == 0) mbar_arrive(bar_kv);
}

constexpr int A2_THREADS = 288;
constexpr int A2_NA = 6;
#define A2_WPRE 4
#define A2_WLEAD 2
#define A2_RPOS 7
constexpr int A2_SM_A = 10 * WO_STAGE;
constexpr int A2_SM_R = A2_SM_A + A2_NA * 16384;
constexpr int A2_SM_BAR = A2_SM_R + 20480;
constexpr int A2_SMEM = A2_SM_BAR + 256 + 1024;

__global__ void __launch_bounds__(A2_THREADS, 1) a2_kernel(const int layer, const __grid_constant__ CUtensorMap tmO, const __grid_constant__ CUtensorMap tmR,
                                                           const __grid_constant__ CUtensorMap tmX1) {
    extern __shared__ unsigned char smraw[];
    const uint32_t sbase = (smem_u32(smraw) + 1023) & ~1023u;
    const uint32_t bars = sbase + A2_SM_BAR, bar_e = bars + 80, bar_r = bars + 128;
    const int tid = threadIdx.x, w = __shfl_sync(~0u, tid >> 5, 0), wg = w >> 2;
    const int tile = sm_tile();
    if (tile >= 128) { sm_idle(2 * layer + 1); return; }
    const int mb = tile >> 3, cg = tile & 7;
    if (wg == 2) {
        const unsigned char* wsrc = reinterpret_cast<const unsigned char*>(g_wo) + cg * 10 * WO_STAGE;
        if (tid == 256) {
            prefetch_tmap(&tmO);
#pragma unroll
            for (int i = 0; i < 17; i++) mbar_init(bars + 8 * i, i >= 10 && i < 16 ? 2 : 1);
            asm volatile("fence.mbarrier_init.release.cluster;" ::: "memory");
#pragma unroll
            for (int kb = 0; kb < A2_WPRE; kb += 2) {
                mbar_expect_tx(bars + 8 * kb, 16384 + 2 * WO_STAGE);
                bulk_load(sbase + kb * WO_STAGE, wsrc + kb * WO_STAGE, 2 * WO_STAGE, bars + 8 * kb);
            }
        }
        __syncwarp();
        asm volatile("bar.arrive 0, 288;" ::: "memory");
        if (tid == 256) {
#pragma unroll
            for (int kb = 0; kb < 10; kb++) if ((kb & 1) || kb >= A2_WPRE) mbar_expect_tx(bars + 8 * kb, (kb & 1) ? 16384 : 16384 + 2 * WO_STAGE);
            mbar_expect_tx(bar_r, 20480);
            pdl_sync();
#pragma unroll 1
            for (int kb = 0; kb < 10; kb++) {
                if (kb >= A2_NA) mbar_wait(bar_e + 8 * (kb - A2_NA), 0);
                tma_load_2d(sbase + A2_SM_A + (kb < A2_NA ? kb : kb - A2_NA) * 16384, &tmO, kb * 64, mb * 128, bars + 8 * kb);
                const int kw = kb + A2_WLEAD;
                if (!(kw & 1) && kw >= A2_WPRE && kw < 10) bulk_load(sbase + kw * WO_STAGE, wsrc + kw * WO_STAGE, 2 * WO_STAGE, bars + 8 * kw);
                if (kb == A2_RPOS) {
                    if (layer == 0) tma_load_2d(sbase + A2_SM_R, &tmR, cg * 80, mb * 128, bar_r);
                    else { tma_load_2d(sbase + A2_SM_R, &tmR, mb * 128, cg * 80, bar_r); tma_load_2d(sbase + A2_SM_R + 10240, &tmR, mb * 128 + 64, cg * 80, bar_r); }
                }
            }
        }
    } else {
        if (tid == 224) { prefetch_tmap(&tmR); prefetch_tmap(&tmX1); sm_started(2 * layer + 1); }
        asm volatile("bar.sync 0, 288;" ::: "memory");
        SPAN(2 + 4 * layer, 0);
        pdl_sync();
        SPAN(2 + 4 * layer, 1);
        TSTAMP2(0);
        TSTAMP4(0);
        if (threadIdx.x == 0) { GSTAMP(g_tim2, 15); }
        const int lane = tid & 31, warp = w, g = lane >> 2, t = lane & 3;
        const int row = layer * SEQ + mb * 128 + 16 * warp + g;
        const unsigned short pv0 = __ldcg(reinterpret_cast<const unsigned short*>(g_piv) + row), pv1 = __ldcg(reinterpret_cast<const unsigned short*>(g_piv) + row + 8);
        float acc[40];
#pragma unroll
        for (int i = 0; i < 40; i++) acc[i] = 0.f;
        const uint64_t da0 = make_desc(sbase + A2_SM_A + wg * 8192, 16, 1024, 1), db0 = make_desc(sbase, 16, 1024, 1);
#pragma unroll 1
        for (int kb = 0; kb < 10; kb++) {
            if (kb == 0) TSTAMP4(11);
            mbar_wait(bars + 8 * kb, 0);
            TSTAMP4(1 + kb);
            wgmma_fence();
#pragma unroll
            for (int kk = 0; kk < 4; kk++) wgmma_n80<0, 0>(acc, da0 + (uint32_t)((kb < A2_NA ? kb : kb - A2_NA) * 1024 + kk * 2), db0 + (uint32_t)(kb * (WO_STAGE / 16) + kk * 2));
            wgmma_commit();
            wgmma_wait<1>();
            if (kb > 0 && kb <= A2_NA && (tid & 127) == 0) mbar_arrive(bar_e + 8 * (kb - 1));
        }
        const uint32_t trow = ((lane & 7) + 8 * (lane >> 4)) * 128 + (((2 * (warp & 3) + ((lane >> 3) & 1)) ^ (lane & 7)) << 4);
        uint32_t xr[10][2];
        mbar_wait(bar_r, 0);
        if (layer == 0) {
#pragma unroll
            for (int j = 0; j < 10; j += 2) ldsm_x4(&xr[j][0], sbase + A2_SM_R + (16 * warp + (lane & 15)) * 160 + (lane >> 4) * 16 + 16 * j);
        } else {
#pragma unroll
            for (int j = 0; j < 10; j += 2) ldsm_x4_t(&xr[j][0], sbase + A2_SM_R + wg * 10240 + trow + 1024 * j);
        }
        mbar_wait(bar_e + 8 * (4 + wg), 0);
        wgmma_wait<0>();
        TSTAMP2(1);
        const float p0 = __uint_as_float((uint32_t)pv0 << 16), p1 = __uint_as_float((uint32_t)pv1 << 16);
        float s[4] = {0.f, 0.f, 0.f, 0.f};
#pragma unroll
        for (int j = 0; j < 10; j++) {
#pragma unroll
            for (int hh = 0; hh < 2; hh++) {
                const uint32_t a = pack2(acc[4 * j + 2 * hh], acc[4 * j + 2 * hh + 1]);
                const __nv_bfloat162 r = __hadd2_rn(*reinterpret_cast<const __nv_bfloat162*>(&xr[j][hh]), *reinterpret_cast<const __nv_bfloat162*>(&a));
                const uint32_t w = *reinterpret_cast<const uint32_t*>(&r);
                xr[j][hh] = w;
                const float d0 = __uint_as_float(w << 16) - (hh ? p1 : p0), d1 = __uint_as_float(w & 0xffff0000u) - (hh ? p1 : p0);
                s[2 * hh] += d0 + d1;
                s[2 * hh + 1] = fmaf(d0, d0, fmaf(d1, d1, s[2 * hh + 1]));
            }
        }
        const uint32_t so = sbase + A2_SM_A + (4 + wg) * 16384;
#pragma unroll
        for (int j = 0; j < 10; j += 2) stsm_x4_t(so + trow + 1024 * j, xr[j][0], xr[j][1], xr[j + 1][0], xr[j + 1][1]);
        fence_async_smem();
        TSTAMP2(2);
#pragma unroll
        for (int o = 1; o <= 2; o <<= 1)
#pragma unroll
            for (int i = 0; i < 4; i++) s[i] += __shfl_xor_sync(~0u, s[i], o);
        if (t < 2) asm volatile("red.relaxed.gpu.global.add.v2.f32 [%0], {%1, %2};" ::"l"(g_sum + layer * SEQ + (g >> 1) * 512 + (mb * 16 + 2 * warp + t) * 2 + (g & 1)), "f"(t ? s[2] : s[0]), "f"(t ? s[3] : s[1]) : "memory");
        if (wg) asm volatile("bar.sync 2, 128;" ::: "memory"); else asm volatile("bar.sync 1, 128;" ::: "memory");
        TSTAMP2(3);
        if ((tid & 127) == 0) tma_store_2d(&tmX1, mb * 128 + 64 * wg, cg * 80, so);
        TSTAMP2(4);
        GSTAMP(g_tim2, 14);
        SPAN(2 + 4 * layer, 3);
    }
}

static int h_nsm;
static void* h_sym[6];
static CUtensorMap h_tmX0, h_tmX1, h_tmOst, h_tmO, h_tmR0, h_tmR1, h_tmX1st, h_tmOut, h_tmWq, h_tmWo;
typedef CUresult (*PFN_encodeTiled)(CUtensorMap*, CUtensorMapDataType, cuuint32_t, void*, const cuuint64_t*, const cuuint64_t*,
                                    const cuuint32_t*, const cuuint32_t*, CUtensorMapInterleave, CUtensorMapSwizzle,
                                    CUtensorMapL2promotion, CUtensorMapFloatOOBfill);
static void make_tmap(CUtensorMap* tm, const void* ptr, uint64_t cols, uint64_t rows, uint32_t bc, uint32_t br, CUtensorMapSwizzle sw, uint64_t pitch = 0) {
    static PFN_encodeTiled fn = nullptr;
    if (!fn) {
        void* p = nullptr; cudaDriverEntryPointQueryResult qr;
        cudaGetDriverEntryPoint("cuTensorMapEncodeTiled", &p, cudaEnableDefault, &qr);
        fn = (PFN_encodeTiled)p;
    }
    if (br == 0) {
        cuuint64_t dims[4] = {cols, 2, rows / 8, 4}; cuuint64_t strides[3] = {cols * 2, cols * 16, cols * 4};
        cuuint32_t box[4] = {bc, 2, 8, 4}; cuuint32_t es[4] = {1, 1, 1, 1};
        fn(tm, CU_TENSOR_MAP_DATA_TYPE_BFLOAT16, 4, const_cast<void*>(ptr), dims, strides, box, es, CU_TENSOR_MAP_INTERLEAVE_NONE, sw,
           CU_TENSOR_MAP_L2_PROMOTION_L2_128B, CU_TENSOR_MAP_FLOAT_OOB_FILL_NONE);
        return;
    }
    cuuint64_t dims[2] = {cols, rows}; cuuint64_t strides[1] = {(pitch ? pitch : cols) * 2};
    cuuint32_t box[2] = {bc, br}; cuuint32_t es[2] = {1, 1};
    fn(tm, CU_TENSOR_MAP_DATA_TYPE_BFLOAT16, 2, const_cast<void*>(ptr), dims, strides, box, es, CU_TENSOR_MAP_INTERLEAVE_NONE, sw,
       CU_TENSOR_MAP_L2_PROMOTION_L2_128B, CU_TENSOR_MAP_FLOAT_OOB_FILL_NONE);
}
template <typename... Args>
static void launch_pdl(void (*kern)(Args...), int grid, int block, int smem, Args... args) {
    cudaLaunchConfig_t cfg = {};
    cfg.gridDim = dim3(grid); cfg.blockDim = dim3(block); cfg.dynamicSmemBytes = smem; cfg.stream = cudaStreamPerThread;
    cudaLaunchAttribute at[1];
    at[0].id = cudaLaunchAttributeProgrammaticStreamSerialization; at[0].val.programmaticStreamSerializationAllowed = 1;
    cfg.attrs = at; cfg.numAttrs = 1;
    cudaLaunchKernelEx(&cfg, kern, args...);
}
static void launch_stage(int k, void* const* d_in, void* d_out) {
    const KgIn kg = {(const bf16*)d_in[4], (const bf16*)d_in[5], (const bf16*)d_in[6], (const bf16*)d_in[7], (const bf16*)d_in[8], (const bf16*)d_in[0], (const bf16*)d_in[1], (const bf16*)d_in[2],
                      (uint4*)h_sym[0], (uint4*)h_sym[1], (uint4*)h_sym[2], (uint4*)h_sym[3], (uint4*)h_sym[4], (float*)h_sym[5]};
    switch (k) {
        case 0: kgen_kernel<<<DM, KG_THREADS, 0, cudaStreamPerThread>>>(kg, h_tmWq, h_tmWo); break;
        case 1: launch_pdl(a1_kernel, h_nsm, A1_THREADS, A1_SMEM, 0, (const bf16*)d_in[0], h_tmX0, h_tmR1, h_tmOst); break;
        case 2: launch_pdl(a2_kernel, h_nsm, A2_THREADS, A2_SMEM, 0, h_tmO, h_tmR0, h_tmX1st); break;
        case 3: launch_pdl(conv_kernel, DM / CV_CPB, CV_THREADS, CV_SMEM, (const bf16*)d_in[9], 0, h_tmOut); break;
        case 5: launch_pdl(a1_kernel, h_nsm, A1_THREADS, A1_SMEM, 1, (const bf16*)d_in[0], h_tmX1, h_tmR1, h_tmOst); break;
        case 6: launch_pdl(a2_kernel, h_nsm, A2_THREADS, A2_SMEM, 1, h_tmO, h_tmR1, h_tmX1st); break;
        case 7: launch_pdl(conv_kernel, DM / CV_CPB, CV_THREADS, CV_SMEM, (const bf16*)d_in[9], 1, h_tmOut); break;
        default: break;
    }
}
static int n_stage_kernels() { return 9; }
static const char* stage_name(int k) { const char* n[] = {"kgen", "a1", "a2", "conv", "tr", "a1", "a2", "conv", "tr"}; return n[k]; }

extern "C" void kernel_launch(void* const* d_in, const int* in_sizes, int n_in, void* d_out, int out_size) {
    (void)in_sizes; (void)n_in; (void)out_size;
    static const void *p_in = nullptr, *p_w1 = nullptr, *p_w2 = nullptr, *p_out = nullptr;
    if (p_in != d_in[0] || p_w1 != d_in[1] || p_w2 != d_in[2] || p_out != d_out) {
        cudaFuncSetAttribute(conv_kernel, cudaFuncAttributeMaxDynamicSharedMemorySize, CV_SMEM);
        cudaFuncSetAttribute(kgen_kernel, cudaFuncAttributePreferredSharedMemoryCarveout, 100);
        cudaFuncSetAttribute(a1_kernel, cudaFuncAttributeMaxDynamicSharedMemorySize, A1_SMEM);
        cudaFuncSetAttribute(a2_kernel, cudaFuncAttributeMaxDynamicSharedMemorySize, A2_SMEM);
        int dev; cudaGetDevice(&dev); cudaDeviceGetAttribute(&h_nsm, cudaDevAttrMultiProcessorCount, dev);
        if (h_nsm != 132) h_nsm = 128;
        cudaGetSymbolAddress(&h_sym[0], g_tap); cudaGetSymbolAddress(&h_sym[1], g_wq); cudaGetSymbolAddress(&h_sym[2], g_wo);
        cudaGetSymbolAddress(&h_sym[3], g_halo); cudaGetSymbolAddress(&h_sym[4], g_sum); cudaGetSymbolAddress(&h_sym[5], g_csp);
        void *po, *px1, *px2;
        cudaGetSymbolAddress(&po, g_o); cudaGetSymbolAddress(&px1, g_x1T); cudaGetSymbolAddress(&px2, g_xcT);
        make_tmap(&h_tmO, po, 640, 2048, 64, 128, CU_TENSOR_MAP_SWIZZLE_128B);
        make_tmap(&h_tmOst, po, 640, 2048, 80, 16, CU_TENSOR_MAP_SWIZZLE_NONE);
        make_tmap(&h_tmX0, d_in[0], 640, 2048, 64, 128, CU_TENSOR_MAP_SWIZZLE_128B);
        make_tmap(&h_tmX1, px2, 2048, 640, 64, 64, CU_TENSOR_MAP_SWIZZLE_128B, XCP);
        make_tmap(&h_tmR0, d_in[0], 640, 2048, 80, 128, CU_TENSOR_MAP_SWIZZLE_NONE);
        make_tmap(&h_tmR1, px2, 2048, 640, 64, 80, CU_TENSOR_MAP_SWIZZLE_128B, XCP);
        make_tmap(&h_tmX1st, px1, 2048, 640, 64, 80, CU_TENSOR_MAP_SWIZZLE_128B, XCP);
        make_tmap(&h_tmWq, d_in[1], 1920, 640, 32, 0, CU_TENSOR_MAP_SWIZZLE_64B);
        make_tmap(&h_tmWo, d_in[2], 640, 640, 32, 0, CU_TENSOR_MAP_SWIZZLE_64B);
        make_tmap(&h_tmOut, d_out, 640, 2048, 80, 8, CU_TENSOR_MAP_SWIZZLE_NONE);
        p_in = d_in[0]; p_w1 = d_in[1]; p_w2 = d_in[2]; p_out = d_out;
    }
    for (int k = 0; k < n_stage_kernels(); k++) launch_stage(k, d_in, d_out);
}
```

```cpp
#include <cuda_runtime.h>
#include <cuda_bf16.h>
#include <stdint.h>
#include <cuda.h>

typedef __nv_bfloat16 bf16;

constexpr int SEQ = 2048;
constexpr int DM = 640;
constexpr int NMODE = 192;

__device__ __forceinline__ float bf2f(bf16 v) { return __bfloat162float(v); }
__device__ __forceinline__ float rbf(float v) {
    uint32_t r;
    asm("cvt.rn.bf16x2.f32 %0, %1, %2;" : "=r"(r) : "f"(v), "f"(0.f));
    return __uint_as_float(r);
}
__device__ __forceinline__ uint32_t pack2(float lo, float hi) {
    __nv_bfloat162 t = __floats2bfloat162_rn(lo, hi);
    return *reinterpret_cast<uint32_t*>(&t);
}
__device__ __forceinline__ void pdl_sync() {
    asm volatile("griddepcontrol.wait;" ::: "memory");
    asm volatile("griddepcontrol.launch_dependents;" ::: "memory");
}
__device__ __forceinline__ float sqrt_apx(float v) { float r; asm("sqrt.approx.ftz.f32 %0, %1;" : "=f"(r) : "f"(v)); return r; }
__device__ __forceinline__ float rcp_apx(float v) { float r; asm("rcp.approx.ftz.f32 %0, %1;" : "=f"(r) : "f"(v)); return r; }
__device__ __forceinline__ uint32_t smem_u32(const void* p) { return (uint32_t)__cvta_generic_to_shared(p); }

constexpr int TPAD = 16;
constexpr int DLEN = 544;
constexpr int TAP_W2 = DLEN * 8, TAP_W3 = TAP_W2 + 768, TAP_C = TAP_W3 + 768, TAPB = TAP_C + 384;
__device__ __align__(128) uint4 g_tap[DM * 128];
#define XPAD 64
constexpr int XCP = SEQ + XPAD;
__device__ __align__(128) bf16 g_x1T[DM * XCP];
__device__ __align__(128) bf16 g_xcT[DM * XCP];
__device__ __align__(128) bf16 g_o[SEQ * DM];
constexpr int WQ_STAGE = 240 * 128, WO_STAGE = 80 * 128;
__device__ __align__(128) uint4 g_wq[8 * 10 * WQ_STAGE / 16];
__device__ __align__(128) uint4 g_wo[8 * 10 * WO_STAGE / 16];
__device__ __align__(16) float g_csp[10 * 1920];
__device__ __align__(16) float2 g_sum[2 * SEQ];
__device__ __align__(16) bf16 g_piv[2 * SEQ];
__device__ __align__(128) bf16 g_yT[DM * XCP];
__device__ uint32_t g_epoch;
__device__ __align__(16) unsigned long long g_rstat[SEQ];
__device__ ulonglong2 g_part[16 * 8 * 128];
__device__ uint4 g_halo[2 * 128 * 320];
__device__ __forceinline__ unsigned long long tagw(uint32_t payload, uint32_t tag) { return ((unsigned long long)tag << 32) | payload; }
__device__ __forceinline__ void st_tag2(ulonglong2* p, uint32_t a, uint32_t b, uint32_t tag) {
    asm volatile("st.global.cg.v2.u64 [%0], {%1, %2};" ::"l"(p), "l"(tagw(a, tag)), "l"(tagw(b, tag)) : "memory");
}
__device__ __forceinline__ ulonglong2 ld_tag2(const ulonglong2* p) {
    ulonglong2 v;
    asm volatile("ld.relaxed.gpu.global.v2.u64 {%0, %1}, [%2];" : "=l"(v.x), "=l"(v.y) : "l"(p) : "memory");
    return v;
}
__device__ __forceinline__ bool tag_ok(ulonglong2 v, uint32_t tag) { return (uint32_t)(v.x >> 32) == tag && (uint32_t)(v.y >> 32) == tag; }
__device__ __forceinline__ uint32_t ld_epoch() { uint32_t v; asm volatile("ld.relaxed.gpu.global.u32 %0, [%1];" : "=r"(v) : "l"(&g_epoch) : "memory"); return v + 1; }
constexpr int SPIN_MAX = 1 << 20;
__device__ uint32_t g_started[4];
__device__ __forceinline__ void sm_started(int slot) { asm volatile("red.relaxed.gpu.global.add.u32 [%0], 1;" ::"l"(g_started + slot) : "memory"); }
__device__ __noinline__ void sm_idle(int slot) {
    if (threadIdx.x) return;
    sm_started(slot);
    const uint32_t want = ld_epoch() * gridDim.x;
    pdl_sync();
#pragma unroll 1
    for (int it = 0; it < SPIN_MAX; it++) {
        uint32_t v;
        asm volatile("ld.relaxed.gpu.global.u32 %0, [%1];" : "=r"(v) : "l"(g_started + slot) : "memory");
        if ((int)(v - want) >= 0) break;
        __nanosleep(100);
    }
}
__device__ __forceinline__ int sm_tile() {
    uint32_t s;
    asm volatile("mov.u32 %0, %smid;" : "=r"(s));
    const uint32_t h = (s - 64) >> 1, q = (h * 37) >> 8;
    const int t0 = ((s >> 1) & 7) * 16 + (s >> 4) * 2 + (s & 1), t1 = (1 + h - 7 * q) * 16 + 8 + q * 2 + (s & 1), t2 = s - 124 < 8 ? s - 116 : 128;
    return gridDim.x == 128 ? (int)blockIdx.x : s < 64 ? t0 : s < 120 ? t1 : t2;
}
#define DBG_SYMS
#define TSTAMP(i)
#define TSTAMP1(i)
#define TSTAMP1T(i, t)
#define TSTAMP1X(i, t)
#define SPAN(k, i)
#define GSTAMP(arr, i)
#define TSTAMP2(i)
#define TSTAMP3(i)
#define TSTAMP4(i)
#define TSTAMPK(i, t)

__device__ __forceinline__ void mma_bf16(float* d, uint32_t a0, uint32_t a1, uint32_t a2, uint32_t a3, uint32_t b0, uint32_t b1) {
    asm volatile("mma.sync.aligned.m16n8k16.row.col.f32.bf16.bf16.f32 {%0,%1,%2,%3}, {%4,%5,%6,%7}, {%8,%9}, {%0,%1,%2,%3};"
                 : "+f"(d[0]), "+f"(d[1]), "+f"(d[2]), "+f"(d[3]) : "r"(a0), "r"(a1), "r"(a2), "r"(a3), "r"(b0), "r"(b1));
}
__device__ __forceinline__ void mma_bf16_k8(float* d, uint32_t a0, uint32_t a1, uint32_t b0) {
    asm volatile("mma.sync.aligned.m16n8k8.row.col.f32.bf16.bf16.f32 {%0,%1,%2,%3}, {%4,%5}, {%6}, {%0,%1,%2,%3};"
                 : "+f"(d[0]), "+f"(d[1]), "+f"(d[2]), "+f"(d[3]) : "r"(a0), "r"(a1), "r"(b0));
}
__device__ __forceinline__ void ldsm_x4(uint32_t* r, uint32_t addr) {
    asm volatile("ldmatrix.sync.aligned.m8n8.x4.shared.b16 {%0,%1,%2,%3}, [%4];"
                 : "=r"(r[0]), "=r"(r[1]), "=r"(r[2]), "=r"(r[3]) : "r"(addr));
}

__device__ __forceinline__ void ldsm_x4_t(uint32_t* r, uint32_t addr) {
    asm volatile("ldmatrix.sync.aligned.m8n8.x4.trans.shared.b16 {%0,%1,%2,%3}, [%4];"
                 : "=r"(r[0]), "=r"(r[1]), "=r"(r[2]), "=r"(r[3]) : "r"(addr));
}
__device__ __forceinline__ void mbar_init(uint32_t bar, int count) { asm volatile("mbarrier.init.shared::cta.b64 [%0], %1;" ::"r"(bar), "r"(count)); }
__device__ __forceinline__ void mbar_arrive(uint32_t bar) { asm volatile("mbarrier.arrive.shared::cta.b64 _, [%0];" ::"r"(bar) : "memory"); }
__device__ __forceinline__ void mbar_wait(uint32_t bar, uint32_t parity) {
    asm volatile("{\n.reg .pred p;\nWAIT_LOOP:\n"
                 "mbarrier.try_wait.parity.shared::cta.b64 p, [%0], %1;\n"
                 "@p bra.uni WAIT_DONE;\nbra.uni WAIT_LOOP;\nWAIT_DONE:\n}" ::"r"(bar), "r"(parity) : "memory");
}

__device__ __forceinline__ void mbar_expect_tx(uint32_t bar, uint32_t bytes) {
    asm volatile("mbarrier.arrive.expect_tx.shared::cta.b64 _, [%0], %1;" ::"r"(bar), "r"(bytes) : "memory");
}
__device__ __forceinline__ void tma_load_2d(uint32_t dst, const void* tmap, int c0, int c1, uint32_t bar) {
    asm volatile("cp.async.bulk.tensor.2d.shared::cluster.global.mbarrier::complete_tx::bytes [%0], [%1, {%3, %4}], [%2];"
                 ::"r"(dst), "l"(tmap), "r"(bar), "r"(c0), "r"(c1) : "memory");
}
__device__ __forceinline__ void fence_async_smem() { asm volatile("fence.proxy.async.shared::cta;" ::: "memory"); }
__device__ __forceinline__ void bulk_load(uint32_t dst, const void* src, uint32_t bytes, uint32_t bar) {
    asm volatile("cp.async.bulk.shared::cluster.global.mbarrier::complete_tx::bytes [%0], [%1], %2, [%3];"
                 ::"r"(dst), "l"(src), "r"(bytes), "r"(bar) : "memory");
}
__device__ __forceinline__ void tma_store_2d(const void* tmap, int c0, int c1, uint32_t src) {
    asm volatile("cp.async.bulk.tensor.2d.global.shared::cta.bulk_group [%0, {%1, %2}], [%3];" ::"l"(tmap), "r"(c0), "r"(c1), "r"(src) : "memory");
    asm volatile("cp.async.bulk.commit_group;" ::: "memory");
    asm volatile("cp.async.bulk.wait_group.read 0;" ::: "memory");
}
__device__ __forceinline__ void stsm_x4(uint32_t addr, uint32_t r0, uint32_t r1, uint32_t r2, uint32_t r3) {
    asm volatile("stmatrix.sync.aligned.m8n8.x4.shared.b16 [%0], {%1,%2,%3,%4};" ::"r"(addr), "r"(r0), "r"(r1), "r"(r2), "r"(r3) : "memory");
}
__device__ __forceinline__ void stsm_x4_t(uint32_t addr, uint32_t r0, uint32_t r1, uint32_t r2, uint32_t r3) {
    asm volatile("stmatrix.sync.aligned.m8n8.x4.trans.shared.b16 [%0], {%1,%2,%3,%4};" ::"r"(addr), "r"(r0), "r"(r1), "r"(r2), "r"(r3) : "memory");
}
__device__ __forceinline__ void prefetch_tmap(const void* tmap) { asm volatile("prefetch.tensormap [%0];" ::"l"(tmap) : "memory"); }

__device__ __forceinline__ float2 cexp_at(float wr2, float wi, float p) {
    float er;
    asm("ex2.approx.ftz.f32 %0, %1;" : "=f"(er) : "f"(wr2 * p));
    float th = wi * p;
    const float k = rintf(th * 0.15915494309189535f);
    th = fmaf(k, -6.2831854820251465f, th);
    th = fmaf(k, 1.7484555314695172e-7f, th);
    return make_float2(er * __cosf(th), er * __sinf(th));
}
__device__ __forceinline__ float2 cmul(float2 a, float2 b) {
    return make_float2(fmaf(a.x, b.x, -a.y * b.y), fmaf(a.x, b.y, a.y * b.x));
}
__device__ __forceinline__ float2 csqr(float2 a) { return make_float2(fmaf(a.x, a.x, -a.y * a.y), (a.x + a.x) * a.y); }
__device__ __forceinline__ uint32_t packh(float2 v) {
    uint32_t r;
    asm("cvt.rn.f16x2.f32 %0, %1, %2;" : "=r"(r) : "f"(v.y), "f"(v.x));
    return r;
}
__device__ __forceinline__ void mma_f16(float* d, uint32_t a0, uint32_t a1, uint32_t a2, uint32_t a3, uint32_t b0, uint32_t b1) {
    asm volatile("mma.sync.aligned.m16n8k16.row.col.f32.f16.f16.f32 {%0,%1,%2,%3}, {%4,%5,%6,%7}, {%8,%9}, {%0,%1,%2,%3};"
                 : "+f"(d[0]), "+f"(d[1]), "+f"(d[2]), "+f"(d[3]) : "r"(a0), "r"(a1), "r"(a2), "r"(a3), "r"(b0), "r"(b1));
}

struct KgIn { const bf16 *logA, *Aim, *Cre, *Cim, *logdt, *x, *wqkv, *wo; uint4 *tap, *wq, *wop, *halo, *sum; float* csp; };
constexpr int KG_THREADS = NMODE / 2;

__global__ void __launch_bounds__(KG_THREADS, 5) kgen_kernel(const KgIn in, const __grid_constant__ CUtensorMap tmWq, const __grid_constant__ CUtensorMap tmWo) {
    __shared__ __align__(8) unsigned long long wbar[3];
    __shared__ __align__(1024) uint4 tab[3 * 896];
    const int d = blockIdx.x, tid = threadIdx.x, lane = tid & 31, warp = __shfl_sync(~0u, tid >> 5, 0);
    SPAN(0, 0); SPAN(0, 1);
    TSTAMPK(0, 0);
    asm volatile("griddepcontrol.launch_dependents;" ::: "memory");
    const bf16 pdt = in.logdt[d];
    const uint32_t pla = reinterpret_cast<const uint32_t*>(in.logA)[d * KG_THREADS + tid], pai = reinterpret_cast<const uint32_t*>(in.Aim)[d * KG_THREADS + tid];
    const uint32_t pcr = reinterpret_cast<const uint32_t*>(in.Cre)[d * KG_THREADS + tid], pci = reinterpret_cast<const uint32_t*>(in.Cim)[d * KG_THREADS + tid];
    const bf16* pfq = tid < 30 ? in.wqkv + (size_t)(d * 30 + tid) * 64 : tid < 40 ? in.wo + (size_t)(d * 10 + tid - 30) * 64 : in.x + (size_t)(d * 32 + tid - 40) * 64;
    if (tid < 72) asm volatile("prefetch.global.L2 [%0];" ::"l"(pfq));
    asm volatile("st.global.v4.u32 [%0], {%1,%1,%1,%1};" ::"l"(in.halo + d * 128 + tid), "r"(~0u));
    if (tid < 32) asm volatile("st.global.v4.u32 [%0], {%1,%1,%1,%1};" ::"l"(in.halo + d * 128 + 96 + tid), "r"(~0u));
    const uint32_t tw = smem_u32(tab) + warp * 14336;
    if (lane == 0) { mbar_init(smem_u32(wbar + warp), 1); prefetch_tmap(d >= 200 ? &tmWo : &tmWq); }
    const int g = lane >> 2, t = lane & 3;
    const uint32_t sta = tw + lane * 128 + ((2 * (lane & 3) + ((lane >> 2) & 1)) << 4);
    const uint32_t lda = tw + t * 128 + ((g ^ (2 * t)) << 4);
    const uint32_t stb = tw + 12288 + lane * 64 + ((4 * ((lane >> 1) & 1) + ((lane >> 2) & 3)) << 3);
    const uint32_t ldb = tw + 12288 + t * 64 + ((g ^ (4 * (t >> 1))) << 3);
    auto sts4 = [&](int e, int off, uint32_t a, uint32_t b, uint32_t c, uint32_t dd) {
        asm volatile("st.shared.v4.u32 [%0], {%1,%2,%3,%4};" ::"r"((sta ^ (e << 4)) + off), "r"(a), "r"(b), "r"(c), "r"(dd) : "memory");
    };
    auto lds4 = [&](int sp, int off, uint32_t* r) {
        asm volatile("ld.shared.v4.u32 {%0,%1,%2,%3}, [%4];" : "=r"(r[0]), "=r"(r[1]), "=r"(r[2]), "=r"(r[3]) : "r"((lda ^ ((sp & 1) << 4)) + sp * 512 + off) : "memory");
    };
    const float dt = rbf(expf(bf2f(pdt)));
    float2 C[2], y1[2], z8[2], y128[2];
    float cmax = 0.f;
#pragma unroll
    for (int m = 0; m < 2; m++) {
        const float wr2 = -rbf(expf(__uint_as_float(m ? pla & 0xffff0000u : pla << 16))) * dt * 1.4426950408889634f;
        const float wi = __uint_as_float(m ? pai & 0xffff0000u : pai << 16) * dt;
        C[m] = make_float2(__uint_as_float(m ? pcr & 0xffff0000u : pcr << 16) * dt, -__uint_as_float(m ? pci & 0xffff0000u : pci << 16) * dt);
        cmax = fmaxf(cmax, fmaxf(fabsf(C[m].x), fabsf(C[m].y)));
        y1[m] = cexp_at(wr2, -wi, 1.f); z8[m] = cexp_at(wr2, wi, 8.f); y128[m] = cexp_at(wr2, -wi, 128.f);
    }
    const int ex = min(max((int)(__reduce_max_sync(~0u, __float_as_uint(cmax)) >> 23), 20), 240);
    const float scale = __uint_as_float((uint32_t)(127 + 10 + 127 - ex) << 23), unscale = 2.0f * __uint_as_float((uint32_t)(ex - 10) << 23);
    TSTAMPK(4, 0);
    float k2048 = 0.f;
    float acc[5][4];
#pragma unroll
    for (int j = 0; j < 5; j++)
#pragma unroll
        for (int k = 0; k < 4; k++) acc[j][k] = 0.f;
    uint32_t af[8][4];
    {
        float2 h0[2], h1[2], g0[2], g1[2], g2[2], g2b[2], g3[2], g4[2], y2[2], y4[2];
#pragma unroll
        for (int m = 0; m < 2; m++) {
            h0[m] = make_float2(1.f, 0.f); h1[m] = csqr(csqr(csqr(z8[m])));
            g0[m] = make_float2(C[m].x * scale, C[m].y * scale);
            g1[m] = cmul(g0[m], y128[m]);
            const float2 y256 = csqr(y128[m]), y512 = csqr(y256);
            g2b[m] = g2[m] = cmul(g0[m], y256); g3[m] = cmul(g0[m], y512); g4[m] = cmul(g3[m], y512);
            y2[m] = csqr(y1[m]); y4[m] = csqr(y2[m]);
            const float2 y1024 = csqr(y512);
            k2048 += fmaf(g4[m].x, y1024.x, -g4[m].y * y1024.y);
        }
#pragma unroll
        for (int e = 0; e < 8; e++) {
            sts4(e, 0, packh(h0[0]), packh(h1[0]), packh(h0[1]), packh(h1[1]));
            sts4(e, 4096, packh(g0[0]), packh(g0[1]), packh(g1[0]), packh(g1[1]));
#pragma unroll
            for (int m = 0; m < 2; m++)
                if (e < 7) { h0[m] = e ? cmul(h0[m], z8[m]) : z8[m]; h1[m] = cmul(h1[m], z8[m]); g0[m] = cmul(g0[m], y1[m]); g1[m] = cmul(g1[m], y1[m]); }
            if (e < 5) k2048 += __shfl_xor_sync(~0u, k2048, 1 << e);
        }
        __syncwarp();
#pragma unroll
        for (int e = 0; e < 8; e++) {
            uint32_t b[4];
            lds4(e, 0, af[e]); lds4(e, 4096, b);
            sts4(e, 8192, packh(g2[0]), packh(g2[1]), packh((e & 1) ? cmul(g3[0], y4[0]) : g3[0]), packh((e & 1) ? cmul(g3[1], y4[1]) : g3[1]));
            asm volatile("st.shared.v2.u32 [%0], {%1,%2};" ::"r"(stb ^ (e << 3)), "r"(packh(g4[0])), "r"(packh(g4[1])) : "memory");
#pragma unroll
            for (int m = 0; m < 2; m++)
                if (e < 7) {
                    g2[m] = e == 3 ? cmul(g2b[m], y128[m]) : cmul(g2[m], y2[m]);
                    if (e & 1) g3[m] = cmul(g3[m], y128[m]);
                    g4[m] = cmul(g4[m], y128[m]);
                }
            mma_f16(acc[0], af[e][0], af[e][1], af[e][2], af[e][3], b[0], b[1]);
            mma_f16(acc[1], af[e][0], af[e][1], af[e][2], af[e][3], b[2], b[3]);
        }
    }
    TSTAMPK(6, 0);
    const int job = d * 3 + warp;
    const bool isq = job < 600;
    const int j2 = isq ? job : job - 600, scol = (j2 / 10) * 32, skb = j2 - (j2 / 10) * 10;
    fence_async_smem();
    __syncwarp();
    if (job < 800) {
        if (lane == 0) {
            mbar_expect_tx(smem_u32(wbar + warp), 4096);
            asm volatile("cp.async.bulk.tensor.4d.shared::cluster.global.mbarrier::complete_tx::bytes [%0], [%1, {%3, %4, %5, %4}], [%2];"
                         ::"r"(tw + 4096), "l"(isq ? &tmWq : &tmWo), "r"(smem_u32(wbar + warp)), "r"(scol), "r"(0), "r"(skb * 8) : "memory");
        }
    } else if (job < 800 + 64) in.sum[(job - 800) * 32 + lane] = make_uint4(0, 0, 0, 0);
#pragma unroll
    for (int sp = 0; sp < 8; sp++) {
        uint32_t c[4], e0, e1;
        lds4(sp, 8192, c);
        asm volatile("ld.shared.v2.u32 {%0,%1}, [%2];" : "=r"(e0), "=r"(e1) : "r"((ldb ^ ((sp & 3) << 3)) + sp * 256) : "memory");
        mma_f16(acc[2], af[sp][0], af[sp][1], af[sp][2], af[sp][3], c[0], c[1]);
        mma_f16(acc[3], af[sp][0], af[sp][1], af[sp][2], af[sp][3], c[2], c[3]);
        mma_f16(acc[4], af[sp][0], af[sp][1], af[sp][2], af[sp][3], e0, e1);
    }
    {
        float* Pp = reinterpret_cast<float*>(tab + warp * 896);
#pragma unroll
        for (int h = 0; h < 2; h++) {
            const int b = g + 8 * h;
            *reinterpret_cast<float2*>(Pp + 8 * b + 2 * t) = make_float2(acc[0][2 * h] * unscale, acc[0][2 * h + 1] * unscale);
            *reinterpret_cast<float2*>(Pp + 128 + 8 * b + 2 * t) = make_float2(acc[1][2 * h] * unscale, acc[1][2 * h + 1] * unscale);
            *reinterpret_cast<float2*>(Pp + 256 + 4 * b + 2 * (t & 1) + 64 * (t >> 1)) = make_float2(acc[2][2 * h] * unscale, acc[2][2 * h + 1] * unscale);
            *reinterpret_cast<float2*>(Pp + 384 + 2 * b + 32 * t) = make_float2(acc[3][2 * h] * unscale, acc[3][2 * h + 1] * unscale);
            Pp[512 + b + 32 * t] = acc[4][2 * h] * unscale;
            Pp[512 + b + 32 * t + 16] = acc[4][2 * h + 1] * unscale;
        }
        if (lane == 0) Pp[640] = k2048 * unscale;
    }
    TSTAMPK(7, 0);
    __syncthreads();
    TSTAMPK(9, 0);
    const float* Kp = reinterpret_cast<const float*>(tab);
    auto ksum = [&](int i) -> float { return (Kp[i] + Kp[3584 + i]) + Kp[7168 + i]; };
    auto ksum4 = [&](int q) -> float4 {
        const float4 a = reinterpret_cast<const float4*>(Kp)[q], b = reinterpret_cast<const float4*>(Kp)[896 + q], c = reinterpret_cast<const float4*>(Kp)[1792 + q];
        return make_float4((a.x + b.x) + c.x, (a.y + b.y) + c.y, (a.z + b.z) + c.z, (a.w + b.w) + c.w);
    };
    {
        uint2* E4 = reinterpret_cast<uint2*>(in.tap + d * 128);
        float4 v = ksum4(tid), u = ksum4(96 + min(tid, 64));
        const float cor = rbf(ksum(tid == 95 ? 384 : 512));
        if (tid == 95) v.w -= cor;
        if (tid == 31) u.w -= cor;
        const uint32_t lo = pack2(v.x, v.y), hi = pack2(v.z, v.w);
        if (tid < 64) {
            E4[6 + tid] = make_uint2(lo, hi);
            E4[(tid < 32 ? 159 : 209 - 32) + tid] = make_uint2(pack2(u.x, u.y), pack2(u.z, u.w));
        } else {
            const uint32_t nx = __shfl_down_sync(~0u, lo, 1);
            in.tap[d * 128 + 35 + tid - 64] = make_uint4(__byte_perm(lo, 0, 0x1010), __byte_perm(lo, hi, 0x5432), __byte_perm(hi, 0, 0x1010), __byte_perm(hi, tid == 95 ? 0u : nx, 0x5432));
            if (tid == 64) E4[241] = make_uint2(pack2(u.x, 0.f), 0u);
        }
    }
    TSTAMPK(10, 0);
    if (job < 800) {
        mbar_wait(smem_u32(wbar + warp), 0);
        const uint32_t src = tw + 4096 + ((lane >> 3) * 16 + (lane & 7)) * 64;
#pragma unroll
        for (int cg = 0; cg < 4; cg++) {
            const int col = scol + 8 * cg, sec = col / DM, r = col - sec * DM, hg = r / 80;
            const int n = isq ? hg * 160 + sec * 80 + r : col;
            unsigned char* dst = (isq ? reinterpret_cast<unsigned char*>(in.wq) + (hg * 9 + skb) * WQ_STAGE : reinterpret_cast<unsigned char*>(in.wop) + (hg * 9 + skb) * WO_STAGE) + (n + g) * 128;
            float cs[4] = {0.f, 0.f, 0.f, 0.f};
#pragma unroll
            for (int h = 0; h < 2; h++) {
                uint32_t w[4];
                ldsm_x4_t(w, src + h * 512 + ((cg ^ ((lane >> 1) & 3)) << 4));
                *reinterpret_cast<uint4*>(dst + (((4 * h + t) ^ g) << 4)) = make_uint4(w[0], w[1], w[2], w[3]);
                if (isq) {
                    mma_bf16(cs, 0x3f803f80u, 0u, 0x3f803f80u, 0u, w[0], w[1]);
                    mma_bf16(cs, 0x3f803f80u, 0u, 0x3f803f80u, 0u, w[2], w[3]);
                }
            }
            if (isq && g == cg) *reinterpret_cast<float2*>(in.csp + skb * 1920 + n + 2 * t) = make_float2(cs[0], cs[1]);
        }
    }
    TSTAMPK(11, 0);
    SPAN(0, 3);
}

#define CV_MODE 0
#define CV_SLEEP 100
constexpr int CV_CPB = 5;
constexpr int CV_THREADS = 512;
constexpr int UPADF = 128;
constexpr int ULEN = UPADF + SEQ + 80;
constexpr int XLEN = SEQ + 16;
constexpr int BX_5 = 0, BX_3 = 3264, BX_9 = 6528, BX_7 = 8960, BX_LEN = 11392;
constexpr int CV_SM_T = 0;
constexpr int CV_SM_B = CV_CPB * TAPB;
constexpr int CV_SM_U = CV_SM_B + CV_CPB * BX_LEN;
constexpr int CV_SM_X = CV_SM_U + CV_CPB * ULEN * 2;
constexpr int CV_SM_Y = CV_SM_X + CV_CPB * XLEN * 2;
constexpr int CV_SM_P = CV_SM_Y + CV_CPB * XLEN * 2;
constexpr int CV_SM_CNT = CV_SM_P + 6 * 4096;
constexpr int CV_SM_O = (CV_SM_CNT + 128 + 127) & ~127;
constexpr int CV_SMEM = CV_SM_O + 20480;
static_assert(CV_SM_B % 128 == 0 && CV_SM_CNT % 16 == 0, "layout");

__device__ __forceinline__ uint32_t ln2(uint32_t x, uint32_t m, float ra, float rb) {
    const __nv_bfloat162 d = __hsub2(*reinterpret_cast<const __nv_bfloat162*>(&x), *reinterpret_cast<const __nv_bfloat162*>(&m));
    const uint32_t w = *reinterpret_cast<const uint32_t*>(&d);
    return pack2(__uint_as_float(w << 16) * ra, __uint_as_float(w & 0xffff0000u) * rb);
}
__device__ __forceinline__ void cp_async16(uint32_t dst, const void* src) {
    asm volatile("cp.async.cg.shared.global [%0], [%1], 16;" ::"r"(dst), "l"(src));
}
__device__ __forceinline__ void cp_async_wait_all() { asm volatile("cp.async.wait_all;" ::: "memory"); }

template <bool FULL>
__device__ __forceinline__ void direct_pass(float (&acc)[8][4], uint32_t ub, uint32_t o0, uint32_t o1, const uint2* __restrict__ Tp, bool first_half) {
    uint32_t sw[8][8];
#pragma unroll
    for (int j = 0; j < 8; j++) { ldsm_x4(&sw[j][0], ub + o0 + j * 256); ldsm_x4(&sw[j][4], ub + o1 + j * 256); }
#pragma unroll
    for (int M = 0; M < 4; M++) {
#pragma unroll
        for (int i = 0; i < 4; i++) {
            const uint2 hi = Tp[128 * M + 16 * i], lo = Tp[128 * M + 16 * i - 8];
#pragma unroll
            for (int j = FULL ? 0 : M; j < 8; j++) mma_bf16(acc[j], hi.x, hi.y, lo.x, lo.y, sw[(j - M) & 7][2 * i], sw[(j - M) & 7][2 * i + 1]);
        }
        if (FULL) {
            ldsm_x4(&sw[7 - M][0], ub + o0 - (M + 1) * 256);
            if (M < 3) ldsm_x4(&sw[7 - M][4], ub + o1 - (M + 1) * 256);
        }
    }
    if (first_half) {
        const uint2 hi = Tp[512], lo = Tp[504];
#pragma unroll
        for (int j = FULL ? 0 : 4; j < 8; j++) mma_bf16(acc[j], hi.x, hi.y, lo.x, lo.y, sw[(j - 4) & 7][0], sw[(j - 4) & 7][1]);
    }
}
__device__ __forceinline__ uint32_t fin2(uint32_t x, uint32_t y, uint32_t u, uint32_t dk) {
    typedef __nv_bfloat162 b2;
    const b2 r = __hadd2_rn(*reinterpret_cast<const b2*>(&x), __hadd2_rn(*reinterpret_cast<const b2*>(&y),
                            __hmul2_rn(*reinterpret_cast<const b2*>(&u), *reinterpret_cast<const b2*>(&dk))));
    return *reinterpret_cast<const uint32_t*>(&r);
}
__global__ void __launch_bounds__(CV_THREADS, 1) conv_kernel(const bf16* __restrict__ Dskip, int layer, const __grid_constant__ CUtensorMap tmOut) {
    extern __shared__ __align__(128) unsigned char sm[];
    SPAN(3 + 4 * layer, 0);
    bf16* Us = reinterpret_cast<bf16*>(sm + CV_SM_U);
    bf16* Xs = reinterpret_cast<bf16*>(sm + CV_SM_X);
    bf16* Ys = reinterpret_cast<bf16*>(sm + CV_SM_Y);
    const int tid = threadIdx.x, lane = tid & 31, warp = __shfl_sync(~0u, tid >> 5, 0);
    const int d0 = blockIdx.x * CV_CPB, tile = blockIdx.x; (void)tile;
    const int g = lane >> 2, ti = lane & 3;
    const int e = g - 2 * ti;
    uint32_t lds_off[4];
    uint32_t off2, off3, offc;
    {
        const int mat = lane >> 3, r = lane & 7;
#pragma unroll
        for (int pr = 0; pr < 4; pr++) {
            const int iw = 2 * pr + (mat >> 1), half = mat & 1;
            const int chunk = (UPADF - 16 * iw + 16 * r + 8 * half) >> 3;
            lds_off[pr] = (uint32_t)((chunk ^ ((chunk >> 3) & 1)) * 16);
        }
        const int j2 = 13 + r + 8 * (mat >> 1), j3 = j2 + 2, i0 = 8 * (mat & 1);
        off2 = (j2 & 1) ? BX_3 + (4 * j2 + i0 + 84) * 2 : BX_5 + (4 * j2 + i0 + 80) * 2;
        off3 = ((j3 & 1) ? BX_7 : BX_9) + (8 * j3 + i0 + 136) * 2;
        const int cc = (UPADF + 16 * (r + (mat >> 1)) + i0) >> 3;
        offc = (uint32_t)((cc ^ ((cc >> 3) & 1)) * 16);
    }
    const uint32_t rtab = warp < 8 ? (warp < 4 ? 0x0B090200u : 0x0C0A0301u) : (warp < 12 ? 0x13111008u : 0x1412241Cu);
    const int rl = (rtab >> (8 * (warp & 3))) & 0xff, type = rl >> 3, c = rl & 7;
    const int H = (type == 1 || type == 2) ? 1 : 0, T0 = 8 * H;
    uint32_t toff = CV_SM_T + c * TAPB + (TPAD + e) * 8;
    uint32_t ubase = smem_u32(Us + c * ULEN);
    const uint32_t bbase = smem_u32(sm + CV_SM_B + c * BX_LEN);
    uint32_t rd0, rd1;
    {
        const uint32_t rstart = warp < 8 ? (warp < 4 ? 0x02000000u : 0x06040000u) : (warp < 12 ? 0x0C0B0A08u : 0x1E1D150Fu);
        const uint32_t rcount = warp < 8 ? 0x02020000u : (warp < 12 ? 0x03010102u : 0x01010806u);
        rd0 = (rstart >> (8 * (warp & 3))) & 0xff; rd1 = rd0 + ((rcount >> (8 * (warp & 3))) & 0xff);
    }
    asm volatile("" : "+r"(lds_off[0]), "+r"(lds_off[1]), "+r"(lds_off[2]), "+r"(lds_off[3]), "+r"(ubase), "+r"(toff), "+r"(rd0), "+r"(rd1));
    const uint2* Tc = reinterpret_cast<const uint2*>(sm + toff);
    TSTAMP1X(9, 256);
    unsigned short dskr;
    asm volatile("ld.global.nc.u16 %0, [%1];" : "=h"(dskr) : "l"(Dskip + d0 + min(lane, CV_CPB - 1)));
    if (tid >= 256) {
        const int t2 = tid - 256;
        if (t2 == 0) {
            mbar_init(smem_u32(sm + CV_SM_CNT) + 104, 1);
            asm volatile("fence.mbarrier_init.release.cluster;" ::: "memory");
            mbar_expect_tx(smem_u32(sm + CV_SM_CNT) + 104, CV_CPB * 2048);
            bulk_load(smem_u32(sm + CV_SM_O), g_tap + d0 * 128, CV_CPB * 2048, smem_u32(sm + CV_SM_CNT) + 104);
        } else if (lane == 0) {
            mbar_init(smem_u32(sm + CV_SM_CNT) + 16 * (warp - 9), warp == 15 ? 16 : 1);
            if (warp < 15) mbar_init(smem_u32(sm + CV_SM_CNT) + 16 * (warp - 9) + 8, 1);
            else if (layer) prefetch_tmap(&tmOut);
        }
        if (t2 < 149) {
            const int k = t2;
            const int off = k < 18 ? BX_5 + 8 * k : k < 37 ? BX_3 + 8 * (k - 18) : k < 69 ? BX_9 + 8 * (k - 37) : k < 101 ? BX_7 + 8 * (k - 69)
                          : k < 133 ? 8 * (k - 101) : (UPADF + SEQ) * 2 + 8 * (k - 133);
#pragma unroll
            for (int c = 0; c < CV_CPB; c++) *reinterpret_cast<uint2*>(sm + (k < 101 ? CV_SM_B + c * BX_LEN : CV_SM_U + c * ULEN * 2) + off) = make_uint2(0, 0);
        }
        asm volatile("bar.sync 1, 256;" ::: "memory");
        TSTAMP1X(10, 256);
        mbar_wait(smem_u32(sm + CV_SM_CNT) + 104, 0);
        TSTAMP1X(11, 256);
#pragma unroll 1
        for (int r = t2; r < 392; r += 256) {
            const bool dd = r < 272, cc = r >= 368;
            const uint32_t* E2 = reinterpret_cast<const uint32_t*>(sm + CV_SM_O) + (dd ? r + 3 : r < 320 ? 301 + 2 * (r - 272) : cc ? 417 : 401 + 2 * (r - 320));
            const uint32_t* E3 = E2 + (dd ? 4 : cc ? 0 : 1);
            const uint32_t s0 = !cc ? 0x7610u : r == 382 ? 0x1044u : 0x4444u, s1 = !cc ? 0x7610u : r == 378 ? 0x1044u : 0x4444u;
            const uint32_t s2 = !cc ? 0x1032u : r == 381 ? 0x4410u : 0x4444u, s3 = !cc ? 0x1032u : r == 377 ? 0x4410u : 0x4444u;
            uint32_t w[CV_CPB][4];
#pragma unroll
            for (int c = 0; c < CV_CPB; c++) { w[c][0] = E2[512 * c]; w[c][1] = E2[512 * c + 1]; w[c][2] = E3[512 * c]; w[c][3] = E3[512 * c + 1]; }
#pragma unroll
            for (int c = 0; c < CV_CPB; c++) {
                const uint32_t a = __byte_perm(w[c][3], w[c][2], s1), b = __byte_perm(w[c][1], w[c][0], s2);
                *reinterpret_cast<uint4*>(sm + CV_SM_T + c * TAPB + r * 16) =
                    make_uint4(__byte_perm(w[c][1], w[c][0], s0), dd || cc ? a : b, dd || cc ? b : a, __byte_perm(w[c][3], w[c][2], s3));
            }
        }
        TSTAMP1X(12, 256);
        if (layer == 0) {
#pragma unroll
            for (int c = 0; c < CV_CPB; c++) reinterpret_cast<uint4*>(g_yT + (size_t)(d0 + c) * XCP)[t2] = make_uint4(~0u, ~0u, ~0u, ~0u);
        }
        pdl_sync();
        if (layer && blockIdx.x == 0 && t2 == 0) g_epoch = ld_epoch();
    } else {
        const uint4* ppv = reinterpret_cast<const uint4*>(g_piv + layer * SEQ) + tid;
        const float4* psv = reinterpret_cast<const float4*>(g_sum + layer * SEQ) + tid;
        const uint4* pxv = reinterpret_cast<const uint4*>(g_x1T + (size_t)d0 * XCP) + tid;
        asm volatile("" : "+l"(ppv), "+l"(psv), "+l"(pxv));
        pdl_sync();
        SPAN(3 + 4 * layer, 1);
        TSTAMP(0);
        if (threadIdx.x == 0) { GSTAMP(g_tim, 15); }
        float4 sv[4];
#pragma unroll
        for (int k = 0; k < 4; k++) sv[k] = __ldcg(psv + 256 * k);
        const uint4 pv = __ldcg(ppv);
        uint4 xv[CV_CPB];
#pragma unroll
        for (int c = 0; c < CV_CPB; c++) xv[c] = __ldcg(pxv + c * (XCP / 8));
        uint32_t mw[4];
        float rs[8];
#pragma unroll
        for (int k = 0; k < 4; k++) {
            const uint32_t pw = k == 0 ? pv.x : k == 1 ? pv.y : k == 2 ? pv.z : pv.w;
            const float d0_ = sv[k].x * (1.0f / DM), d1_ = sv[k].z * (1.0f / DM);
            mw[k] = pack2(__uint_as_float(pw << 16) + d0_, __uint_as_float(pw & 0xffff0000u) + d1_);
            const uint32_t vr = pack2(fmaxf(fmaf(-d0_, d0_, sv[k].y * (1.0f / DM)), 0.f), fmaxf(fmaf(-d1_, d1_, sv[k].w * (1.0f / DM)), 0.f));
            const uint32_t ve = pack2(__uint_as_float(vr << 16) + 1e-5f, __uint_as_float(vr & 0xffff0000u) + 1e-5f);
            const uint32_t sd = pack2(sqrt_apx(__uint_as_float(ve << 16)), sqrt_apx(__uint_as_float(ve & 0xffff0000u)));
            rs[2 * k] = rcp_apx(__uint_as_float(sd << 16)); rs[2 * k + 1] = rcp_apx(__uint_as_float(sd & 0xffff0000u));
        }
        if (rs[0] != 123.f) TSTAMP(13);
        const int ch = tid + UPADF / 8, pch = ch ^ ((ch >> 3) & 1);
#pragma unroll
        for (int c = 0; c < CV_CPB; c++) {
            *reinterpret_cast<uint4*>(Xs + c * XLEN + tid * 8) = xv[c];
            *reinterpret_cast<uint4*>(Us + c * ULEN + pch * 8) =
                make_uint4(ln2(xv[c].x, mw[0], rs[0], rs[1]), ln2(xv[c].y, mw[1], rs[2], rs[3]), ln2(xv[c].z, mw[2], rs[4], rs[5]), ln2(xv[c].w, mw[3], rs[6], rs[7]));
        }
    }
    __syncthreads();
    TSTAMP(1);
#pragma unroll 1
    for (int rd = rd0; rd < (int)rd1; rd++) {
        const int i = 32 * rd + lane;
        if (i < CV_CPB * 193) {
            const int c = i / 193, chunk = i - c * 193 - 1, ch = chunk + UPADF / 8;
            const bf16* uc = Us + c * ULEN;
            const uint4 o = *reinterpret_cast<const uint4*>(uc + (ch ^ ((ch >> 3) & 1)) * 8);
            const uint2 lo = *reinterpret_cast<const uint2*>(uc + ((ch - 1) ^ (((ch - 1) >> 3) & 1)) * 8 + 4);
            const uint2 hi = *reinterpret_cast<const uint2*>(uc + ((ch + 1) ^ (((ch + 1) >> 3) & 1)) * 8);
            const uint32_t w[8] = {lo.x, lo.y, o.x, o.y, o.z, o.w, hi.x, hi.y};
            float v[16], b[8];
#pragma unroll
            for (int k = 0; k < 8; k++) { v[2 * k] = __uint_as_float(w[k] << 16); v[2 * k + 1] = __uint_as_float(w[k] & 0xffff0000u); }
            unsigned char* bx = sm + CV_SM_B + c * BX_LEN + chunk * 16;
#pragma unroll
            for (int k = 0; k < 8; k++) b[k] = v[k + 4] + (v[k + 3] + v[k + 5]);
            *reinterpret_cast<uint2*>(bx + BX_3 + 168) = make_uint2(pack2(b[0], b[1]), pack2(b[2], b[3]));
            *reinterpret_cast<uint2*>(bx + BX_3 + 176) = make_uint2(pack2(b[4], b[5]), pack2(b[6], b[7]));
#pragma unroll
            for (int k = 0; k < 8; k++) b[k] += v[k + 2] + v[k + 6];
            *reinterpret_cast<uint4*>(bx + BX_5 + 160) = make_uint4(pack2(b[0], b[1]), pack2(b[2], b[3]), pack2(b[4], b[5]), pack2(b[6], b[7]));
            if (chunk < 128) {
#pragma unroll
                for (int k = 0; k < 8; k++) b[k] += v[k + 1] + v[k + 7];
                *reinterpret_cast<uint4*>(bx + BX_7 + 272) = make_uint4(pack2(b[0], b[1]), pack2(b[2], b[3]), pack2(b[4], b[5]), pack2(b[6], b[7]));
#pragma unroll
                for (int k = 0; k < 8; k++) b[k] += v[k] + v[k + 8];
                *reinterpret_cast<uint4*>(bx + BX_9 + 272) = make_uint4(pack2(b[0], b[1]), pack2(b[2], b[3]), pack2(b[4], b[5]), pack2(b[6], b[7]));
            }
        }
    }
    __syncwarp();
    if (lane == 0) mbar_arrive(smem_u32(sm + CV_SM_CNT) + 96);
    TSTAMP(2);
    {
        float acc[8][4];
#pragma unroll
        for (int j = 0; j < 8; j++)
#pragma unroll
            for (int k = 0; k < 4; k++) acc[j][k] = 0.f;
#pragma unroll 1
        for (int pass = (type == 2 || type == 4) ? 1 : 0; pass < ((type == 1 || type == 3) ? 1 : 2); pass++) {
            const uint32_t o0 = pass ? lds_off[2] : lds_off[0], o1 = pass ? lds_off[3] : lds_off[1];
            if (H) direct_pass<true>(acc, ubase + T0 * 256, o0, o1, Tc + 64 * pass, pass == 0);
            else direct_pass<false>(acc, ubase, o0, o1, Tc + 64 * pass, pass == 0);
        }
        TSTAMP(6);
        mbar_wait(smem_u32(sm + CV_SM_CNT) + 96, 0);
        if (type != 1 && type != 4) {
            const uint32_t* w2 = reinterpret_cast<const uint32_t*>(sm + CV_SM_T + c * TAPB + TAP_W2) + (115 - 96) + 4 * g - 2 * ti;
            uint32_t f[10][2];
#pragma unroll
            for (int k = 0; k < 10; k++) { f[k][0] = w2[16 * k]; f[k][1] = w2[16 * k - 8]; }
            const uint32_t ab = bbase + off2 + (2 * T0 + 6) * 128;
            const int kmax = H ? 23 : 8;
            uint32_t a[3][4];
            ldsm_x4_t(a[0], ab);
            ldsm_x4_t(a[1], ab - 128);
#pragma unroll
            for (int kp = 0; kp < 24; kp++) {
                if (kp > kmax) break;
                if (kp < 22) ldsm_x4_t(a[(kp + 2) % 3], ab - min(kp + 2, kmax) * 128);
#pragma unroll
                for (int j = 0; j < 8; j++) {
                    const int ee = 2 * j - 14 + kp;
                    if (ee >= 0 && ee <= 9) mma_bf16(acc[j], a[kp % 3][0], a[kp % 3][1], a[kp % 3][2], a[kp % 3][3], f[ee][0], f[ee][1]);
                }
            }
        }
        TSTAMP(7);
        if (type != 2 && type != 4) {
            const uint32_t* w3 = reinterpret_cast<const uint32_t*>(sm + CV_SM_T + c * TAPB + TAP_W3) + (129 - 96) + 2 * (g - ti);
            uint32_t f[9][2];
#pragma unroll
            for (int k = 0; k < 9; k++) { f[k][0] = w3[16 * k]; f[k][1] = w3[16 * k - 8]; }
            const uint32_t ab = bbase + off3 + (T0 - 2) * 256;
            uint32_t a[3][4];
            ldsm_x4_t(a[0], ab);
            ldsm_x4_t(a[1], ab - H * 256);
#pragma unroll
            for (int kp = 0; kp < 9; kp++) {
                if (kp > T0) break;
                if (kp < 7) ldsm_x4_t(a[(kp + 2) % 3], ab - min(kp + 2, T0) * 256);
#pragma unroll
                for (int j = 0; j < 8; j++) {
                    const int dl = j - 7 + kp;
                    if (dl >= 0 && dl <= 8) mma_bf16(acc[j], a[kp % 3][0], a[kp % 3][1], a[kp % 3][2], a[kp % 3][3], f[dl][0], f[dl][1]);
                }
            }
            const uint2* Dc = reinterpret_cast<const uint2*>(sm + CV_SM_T + c * TAPB + TAP_C) + e;
            const uint2 h63 = Dc[16], h64 = Dc[32], l63 = Dc[8], l64 = Dc[24];
#pragma unroll
            for (int j = 0; j < 8; j++)
                if (j == 7 || H) {
                    uint32_t bq[4];
                    ldsm_x4(bq, ubase + offc + (T0 + j - 8) * 256);
                    mma_bf16(acc[j], h64.x, h64.y, l64.x, l64.y, bq[0], bq[1]);
                    mma_bf16(acc[j], h63.x, h63.y, l63.x, l63.y, bq[2], bq[3]);
                }
        }
        TSTAMP(8);
        const bool hi_half = (type == 2 || type == 4);
        if (type != 0) {
            const int pair = H ? c : 5;
            float4* give = reinterpret_cast<float4*>(sm + CV_SM_P + pair * 4096 + (hi_half ? 2048 : 0)) + lane;
            const float4* take = reinterpret_cast<const float4*>(sm + CV_SM_P + pair * 4096 + (hi_half ? 0 : 2048)) + lane;
            const uint32_t pb = smem_u32(sm + CV_SM_CNT) + pair * 16;
#pragma unroll
            for (int j = 0; j < 4; j++)
                give[32 * j] = hi_half ? make_float4(acc[j][0], acc[j][1], acc[j][2], acc[j][3]) : make_float4(acc[j + 4][0], acc[j + 4][1], acc[j + 4][2], acc[j + 4][3]);
            __syncwarp();
            if (lane == 0) mbar_arrive(pb + (hi_half ? 8 : 0));
            mbar_wait(pb + (hi_half ? 0 : 8), 0);
#pragma unroll
            for (int j = 0; j < 4; j++) {
                const float4 v = take[32 * j];
                acc[j][0] = (hi_half ? acc[j + 4][0] : acc[j][0]) + v.x; acc[j][1] = (hi_half ? acc[j + 4][1] : acc[j][1]) + v.y;
                acc[j][2] = (hi_half ? acc[j + 4][2] : acc[j][2]) + v.z; acc[j][3] = (hi_half ? acc[j + 4][3] : acc[j][3]) + v.w;
            }
        }
        const uint32_t dk = __shfl_sync(~0u, (uint32_t)dskr, c) * 0x10001u;
#pragma unroll 1
        for (int rnd = 0; rnd < (type == 0 ? 2 : 1); rnd++) {
            const int Q = 2 * H + (hi_half ? 1 : rnd);
            if (rnd) {
#pragma unroll
                for (int j = 0; j < 4; j++)
#pragma unroll
                    for (int k = 0; k < 4; k++) acc[j][k] = acc[j + 4][k];
            }
            const uint32_t ya = smem_u32(Ys + c * XLEN) + (128 * (4 * Q + (lane >> 4)) + 16 * (lane & 7) + 8 * ((lane >> 3) & 1)) * 2;
#pragma unroll
            for (int j = 0; j < 4; j += 2)
                asm volatile("stmatrix.sync.aligned.m8n8.x4.trans.shared.b16 [%0], {%1,%2,%3,%4};" ::"r"(ya + j * 256),
                             "r"(pack2(acc[j][0], acc[j][1])), "r"(pack2(acc[j][2], acc[j][3])),
                             "r"(pack2(acc[j + 1][0], acc[j + 1][1])), "r"(pack2(acc[j + 1][2], acc[j + 1][3])) : "memory");
            __syncwarp();
            uint4 yv[2], xv[2], uv[2];
#pragma unroll
            for (int k = 0; k < 2; k++) {
                const int t = 512 * Q + 256 * k + 8 * lane, cu = (t + UPADF) >> 3;
                yv[k] = *reinterpret_cast<const uint4*>(Ys + c * XLEN + t);
                xv[k] = *reinterpret_cast<const uint4*>(Xs + c * XLEN + t);
                uv[k] = *reinterpret_cast<const uint4*>(Us + c * ULEN + (cu ^ ((cu >> 3) & 1)) * 8);
            }
#pragma unroll
            for (int k = 0; k < 2; k++)
                asm volatile("st.relaxed.gpu.global.v4.u32 [%0], {%1,%2,%3,%4};" ::"l"((layer ? g_yT : g_xcT) + (size_t)(d0 + c) * XCP + 512 * Q + 256 * k + 8 * lane),
                             "r"(fin2(xv[k].x, yv[k].x, uv[k].x, dk)), "r"(fin2(xv[k].y, yv[k].y, uv[k].y, dk)), "r"(fin2(xv[k].z, yv[k].z, uv[k].z, dk)), "r"(fin2(xv[k].w, yv[k].w, uv[k].w, dk)) : "memory");
        }
        TSTAMP(4);
        if (layer == 1) {
            const int mb = blockIdx.x >> 3, cg = blockIdx.x & 7;
            const bf16* src = g_yT + (size_t)(cg * 80 + (tid >> 4)) * XCP + mb * 128 + (tid & 15) * 8;
            uint32_t v[3][4];
            __syncthreads();
            TSTAMP(5);
            uint32_t todo = warp < 8 ? 7 : 3;
#pragma unroll 1
            for (int it = 0; it < SPIN_MAX; it++) {
#pragma unroll
                for (int k = 0; k < 3; k++)
                    if (todo >> k & 1)
                        asm volatile("ld.relaxed.gpu.global.v4.u32 {%0,%1,%2,%3}, [%4];" : "=r"(v[k][0]), "=r"(v[k][1]), "=r"(v[k][2]), "=r"(v[k][3]) : "l"(src + k * (32 * XCP)) : "memory");
#pragma unroll
                for (int k = 0; k < 3; k++)
                    if ((todo >> k & 1) && v[k][0] != ~0u && v[k][1] != ~0u && v[k][2] != ~0u && v[k][3] != ~0u) {
                        *reinterpret_cast<uint4*>(sm + (32 * k + (tid >> 4)) * 272 + (tid & 15) * 16) = make_uint4(v[k][0], v[k][1], v[k][2], v[k][3]);
                        todo ^= 1u << k;
                    }
                if (!todo) break;
                __nanosleep(CV_SLEEP);
            }
            __syncthreads();
            uint32_t w[12];
#pragma unroll
            for (int k = 0; k < 3; k++) ldsm_x4(&w[4 * k], smem_u32(sm) + min(32 * k + lane, 79) * 272 + warp * 16);
            const uint32_t ot = smem_u32(sm + CV_SM_O) + warp * 1280, oa = ot + (lane & 7) * 160 + (lane >> 3) * 16;
            stsm_x4_t(oa, w[0], w[1], w[2], w[3]);
            stsm_x4_t(oa + 64, w[4], w[5], w[6], w[7]);
            asm volatile("stmatrix.sync.aligned.m8n8.x2.trans.shared.b16 [%0], {%1,%2};" ::"r"(oa + 128), "r"(w[8]), "r"(w[9]) : "memory");
            fence_async_smem();
            __syncwarp();
            if (lane == 0) tma_store_2d(&tmOut, cg * 80, mb * 128 + 8 * warp, ot);
        }
    }
    TSTAMP(3);
    GSTAMP(g_tim, 14);
    SPAN(3 + 4 * layer, 3);
}

__device__ __forceinline__ void wgmma_fence() { asm volatile("wgmma.fence.sync.aligned;" ::: "memory"); }
__device__ __forceinline__ void wgmma_commit() { asm volatile("wgmma.commit_group.sync.aligned;" ::: "memory"); }
template <int N> __device__ __forceinline__ void wgmma_wait() { asm volatile("wgmma.wait_group.sync.aligned %0;" ::"n"(N) : "memory"); }
__device__ __forceinline__ uint64_t make_desc(uint32_t addr, uint32_t lbo, uint32_t sbo, uint32_t mode) {
    return (uint64_t)((addr & 0x3FFFF) >> 4) | ((uint64_t)(lbo >> 4) << 16) | ((uint64_t)(sbo >> 4) << 32) | ((uint64_t)mode << 62);
}
template <int TA, int TB>
__device__ __forceinline__ void wgmma_n240(float (&d)[120], uint64_t da, uint64_t db) {
    asm volatile("wgmma.mma_async.sync.aligned.m64n240k16.f32.bf16.bf16 {%0,%1,%2,%3,%4,%5,%6,%7,%8,%9,%10,%11,%12,%13,%14,%15,%16,%17,%18,%19,%20,%21,%22,%23,%24,%25,%26,%27,%28,%29,%30,%31,%32,%33,%34,%35,%36,%37,%38,%39,%40,%41,%42,%43,%44,%45,%46,%47,%48,%49,%50,%51,%52,%53,%54,%55,%56,%57,%58,%59,%60,%61,%62,%63,%64,%65,%66,%67,%68,%69,%70,%71,%72,%73,%74,%75,%76,%77,%78,%79,%80,%81,%82,%83,%84,%85,%86,%87,%88,%89,%90,%91,%92,%93,%94,%95,%96,%97,%98,%99,%100,%101,%102,%103,%104,%105,%106,%107,%108,%109,%110,%111,%112,%113,%114,%115,%116,%117,%118,%119}, %120, %121, 1, 1, 1, %122, %123;"
                 : "+f"(d[0]), "+f"(d[1]), "+f"(d[2]), "+f"(d[3]), "+f"(d[4]), "+f"(d[5]), "+f"(d[6]), "+f"(d[7]), "+f"(d[8]), "+f"(d[9]), "+f"(d[10]), "+f"(d[11]), "+f"(d[12]), "+f"(d[13]), "+f"(d[14]), "+f"(d[15]), "+f"(d[16]), "+f"(d[17]), "+f"(d[18]), "+f"(d[19]), "+f"(d[20]), "+f"(d[21]), "+f"(d[22]), "+f"(d[23]), "+f"(d[24]), "+f"(d[25]), "+f"(d[26]), "+f"(d[27]), "+f"(d[28]), "+f"(d[29]), "+f"(d[30]), "+f"(d[31]), "+f"(d[32]), "+f"(d[33]), "+f"(d[34]), "+f"(d[35]), "+f"(d[36]), "+f"(d[37]), "+f"(d[38]), "+f"(d[39]), "+f"(d[40]), "+f"(d[41]), "+f"(d[42]), "+f"(d[43]), "+f"(d[44]), "+f"(d[45]), "+f"(d[46]), "+f"(d[47]), "+f"(d[48]), "+f"(d[49]), "+f"(d[50]), "+f"(d[51]), "+f"(d[52]), "+f"(d[53]), "+f"(d[54]), "+f"(d[55]), "+f"(d[56]), "+f"(d[57]), "+f"(d[58]), "+f"(d[59]), "+f"(d[60]), "+f"(d[61]), "+f"(d[62]), "+f"(d[63]), "+f"(d[64]), "+f"(d[65]), "+f"(d[66]), "+f"(d[67]), "+f"(d[68]), "+f"(d[69]), "+f"(d[70]), "+f"(d[71]), "+f"(d[72]), "+f"(d[73]), "+f"(d[74]), "+f"(d[75]), "+f"(d[76]), "+f"(d[77]), "+f"(d[78]), "+f"(d[79]), "+f"(d[80]), "+f"(d[81]), "+f"(d[82]), "+f"(d[83]), "+f"(d[84]), "+f"(d[85]), "+f"(d[86]), "+f"(d[87]), "+f"(d[88]), "+f"(d[89]), "+f"(d[90]), "+f"(d[91]), "+f"(d[92]), "+f"(d[93]), "+f"(d[94]), "+f"(d[95]), "+f"(d[96]), "+f"(d[97]), "+f"(d[98]), "+f"(d[99]), "+f"(d[100]), "+f"(d[101]), "+f"(d[102]), "+f"(d[103]), "+f"(d[104]), "+f"(d[105]), "+f"(d[106]), "+f"(d[107]), "+f"(d[108]), "+f"(d[109]), "+f"(d[110]), "+f"(d[111]), "+f"(d[112]), "+f"(d[113]), "+f"(d[114]), "+f"(d[115]), "+f"(d[116]), "+f"(d[117]), "+f"(d[118]), "+f"(d[119])
                 : "l"(da), "l"(db), "n"(TA), "n"(TB));
}

template <int TA, int TB>
__device__ __forceinline__ void wgmma_n80(float (&d)[40], uint64_t da, uint64_t db) {
    asm volatile("wgmma.mma_async.sync.aligned.m64n80k16.f32.bf16.bf16 {%0,%1,%2,%3,%4,%5,%6,%7,%8,%9,%10,%11,%12,%13,%14,%15,%16,%17,%18,%19,%20,%21,%22,%23,%24,%25,%26,%27,%28,%29,%30,%31,%32,%33,%34,%35,%36,%37,%38,%39}, %40, %41, 1, 1, 1, %42, %43;"
                 : "+f"(d[0]), "+f"(d[1]), "+f"(d[2]), "+f"(d[3]), "+f"(d[4]), "+f"(d[5]), "+f"(d[6]), "+f"(d[7]), "+f"(d[8]), "+f"(d[9]), "+f"(d[10]), "+f"(d[11]), "+f"(d[12]), "+f"(d[13]), "+f"(d[14]), "+f"(d[15]), "+f"(d[16]), "+f"(d[17]), "+f"(d[18]), "+f"(d[19]), "+f"(d[20]), "+f"(d[21]), "+f"(d[22]), "+f"(d[23]), "+f"(d[24]), "+f"(d[25]), "+f"(d[26]), "+f"(d[27]), "+f"(d[28]), "+f"(d[29]), "+f"(d[30]), "+f"(d[31]), "+f"(d[32]), "+f"(d[33]), "+f"(d[34]), "+f"(d[35]), "+f"(d[36]), "+f"(d[37]), "+f"(d[38]), "+f"(d[39])
                 : "l"(da), "l"(db), "n"(TA), "n"(TB));
}

constexpr int A1_THREADS = 384;
constexpr int A1_NST = 4;
#define A1_PRE0 2
#define A1_SKEW 8
#define A1_PRE1 1
constexpr int A1_STAGE = 16384 + WQ_STAGE;
constexpr int A1_KVP = 336;
constexpr int A1_SM_KV = 2 * A1_STAGE;
constexpr int A1_SM_O = A1_SM_KV + 144 * A1_KVP;
constexpr int A1_SM_BAR = A1_NST * A1_STAGE;
constexpr int A1_SM_CS = A1_SM_BAR + 256;
constexpr int A1_SM_RS = A1_SM_CS + 1024;
constexpr int A1_SMEM = A1_SM_RS + 1024 + 1024;
static_assert(A1_SM_O % 128 == 0 && A1_SM_O + 20480 <= A1_SM_BAR, "layout");

template <int L>
__device__ __forceinline__ void a1_mainloop(float (&acc)[120], uint32_t sbase, uint32_t bars, int wg, int tile) {
    constexpr int layer = L; (void)layer;
    const uint64_t da0 = L ? make_desc(sbase + wg * 8192, 8192, 1024, 1) : make_desc(sbase + wg * 8192, 16, 1024, 1), db0 = make_desc(sbase + 16384, 16, 1024, 1);
#pragma unroll 1
    for (int t = 0; t < 10; t++) {
        const int st = t % A1_NST;
        mbar_wait(bars + 8 * st, (t / A1_NST) & 1);
        if (t == A1_SKEW && wg == 0) mbar_wait(bars + 160, 0);
        TSTAMP3(1 + t);
        wgmma_fence();
#pragma unroll
        for (int kk = 0; kk < 4; kk++) wgmma_n240<L, 0>(acc, da0 + (uint32_t)(st * (A1_STAGE / 16) + kk * (L ? 128 : 2)), db0 + (uint32_t)(st * (A1_STAGE / 16) + kk * 2));
        wgmma_commit();
        if (t == 9 && threadIdx.x == 128) { mbar_arrive(bars + 160); mbar_arrive(bars + 144); }
        if (t == A1_SKEW - 1 && wg == 0) wgmma_wait<0>(); else wgmma_wait<1>();
        if (t > 0 && t < 9 && (threadIdx.x & 127) == 0) {
            if (t != A1_SKEW || wg) mbar_arrive(bars + 8 * (A1_NST + (t - 1) % A1_NST));
            if (t == A1_SKEW - 1 && wg == 0) mbar_arrive(bars + 8 * (A1_NST + t % A1_NST));
        }
    }
}

__global__ void __launch_bounds__(A1_THREADS, 1) a1_kernel(const int layer, const bf16* __restrict__ x0, const __grid_constant__ CUtensorMap tmX,
                                                           const __grid_constant__ CUtensorMap tmOst) {
    extern __shared__ unsigned char smraw[];
    const uint32_t sbase = (smem_u32(smraw) + 1023) & ~1023u;
    const uint32_t bars = sbase + A1_SM_BAR;
    const uint32_t bar_stat = bars + 64, bar_kv = bars + 72, bar_rd = bars + 168;
    const int tid = threadIdx.x, w = __shfl_sync(~0u, tid >> 5, 0), wg = w >> 2;
    const int tile = sm_tile();
    if (tile >= 128) { sm_idle(2 * layer); return; }
    const int mb = (tile >> 2) & 15, hg = 4 * (tile >> 6) + (tile & 3);
    unsigned char* stg = smraw + (sbase - smem_u32(smraw));
    float* cs = reinterpret_cast<float*>(stg + A1_SM_CS);
    float2* rst = reinterpret_cast<float2*>(stg + A1_SM_RS);
    const int pre = layer ? A1_PRE1 : A1_PRE0;
    auto issue_w = [&](int it) {
        const int kb = it + 5 * (hg >> 2) - (it + 5 * (hg >> 2) >= 10 ? 10 : 0);
        bulk_load(sbase + (it % A1_NST) * A1_STAGE + 16384, reinterpret_cast<const unsigned char*>(g_wq) + (hg * 10 + kb) * WQ_STAGE, WQ_STAGE, bars + 8 * (it % A1_NST));
    };
    auto issue_x = [&](int it) {
        const int kb = it + 5 * (hg >> 2) - (it + 5 * (hg >> 2) >= 10 ? 10 : 0);
        const uint32_t dst = sbase + (it % A1_NST) * A1_STAGE, full = bars + 8 * (it % A1_NST);
        if (layer == 0) tma_load_2d(dst, &tmX, kb * 64, mb * 128, full);
        else { tma_load_2d(dst, &tmX, mb * 128, kb * 64, full); tma_load_2d(dst + 8192, &tmX, mb * 128 + 64, kb * 64, full); }
    };
    if (w == 8) {
        if (tid == 256) {
            prefetch_tmap(&tmX);
#pragma unroll
            for (int i = 0; i < A1_NST; i++) { mbar_init(bars + 8 * i, 1); mbar_init(bars + 8 * (A1_NST + i), 2); }
            asm volatile("fence.mbarrier_init.release.cluster;" ::: "memory");
#pragma unroll
            for (int i = 0; i < A1_NST; i++) mbar_expect_tx(bars + 8 * i, A1_STAGE);
        }
        __syncwarp();
        asm volatile("bar.arrive 0, 384;" ::: "memory");
        if (tid == 256) {
#pragma unroll 1
            for (int kb = 0; kb < pre; kb++) { if (layer) issue_w(kb); else issue_x(kb); }
            pdl_sync();
#pragma unroll 1
            for (int kb = 0; kb < A1_NST; kb++) {
                if (kb >= pre || layer) issue_x(kb);
                if (kb >= pre || !layer) issue_w(kb);
            }
        }
    } else {
        if (tid == 0) {
            mbar_init(bar_stat, 3);
#pragma unroll
            for (int i = 0; i < 9; i++) mbar_init(bar_kv + 8 * i, i ? 1 : 4);
            mbar_init(bars + 144, 1);
            mbar_init(bars + 160, 1);
#pragma unroll
            for (int i = 0; i < 5; i++) mbar_init(bar_rd + 8 * i, 2);
            asm volatile("fence.mbarrier_init.release.cluster;" ::: "memory");
        } else if (tid == 320) prefetch_tmap(&tmOst);
        asm volatile("bar.sync 0, 384;" ::: "memory");
    }
    SPAN(1 + 4 * layer, 0);
    const uint32_t tag = ld_epoch();
    if (tid == 352) sm_started(2 * layer);
    constexpr int on = 1;
    if (wg == 2) {
        if (w == 9) {
            if (layer == 0) pdl_sync();
            float4 a[2] = {};
#pragma unroll
            for (int k = 0; k < 10; k++)
#pragma unroll
                for (int h = 0; h < 2; h++) {
                    const float4 v = __ldcg(reinterpret_cast<const float4*>(g_csp + k * 1920 + hg * 240) + min(tid - 288 + 32 * h, 59));
                    a[h].x += v.x; a[h].y += v.y; a[h].z += v.z; a[h].w += v.w;
                }
            reinterpret_cast<float4*>(cs)[tid - 288] = a[0];
            reinterpret_cast<float4*>(cs)[min(tid - 256, 59)] = a[1];
            __syncwarp();
            if (tid == 288) mbar_arrive(bar_stat);
        } else if (w == 8) {
            if (tid == 256) {
#pragma unroll 1
                for (int kb = A1_NST; kb < 10; kb++) {
                    mbar_wait(bars + 8 * (A1_NST + kb % A1_NST), ((kb / A1_NST) - 1) & 1);
                    if (layer && kb < 9) mbar_wait(bar_rd + 8 * (kb - A1_NST), 0);
                    mbar_expect_tx(bars + 8 * (kb % A1_NST), A1_STAGE);
                    issue_x(kb); issue_w(kb);
                }
                TSTAMP1T(6, 256);
            }
            __syncwarp();
        } else {
            const int j = tid - 320;
            if (layer == 0) {
                const uint4* src = reinterpret_cast<const uint4*>(x0 + (size_t)(mb * 128 + hg * 16 + (j >> 2)) * DM);
                uint4 v[20];
#pragma unroll
                for (int k = 0; k < 20; k++) v[k] = __ldg(src + (j & 3) + 4 * k);
                const float p0 = __uint_as_float(__shfl_sync(~0u, v[0].x, j & 28) << 16);
                float s[2] = {0.f, 0.f}, q[2] = {0.f, 0.f};
#pragma unroll
                for (int k = 0; k < 20; k++) {
                    const uint32_t w[4] = {v[k].x, v[k].y, v[k].z, v[k].w};
#pragma unroll
                    for (int i = 0; i < 4; i++) {
                        const float a = __uint_as_float(w[i] << 16) - p0, b = __uint_as_float(w[i] & 0xffff0000u) - p0;
                        s[0] += a; s[1] += b; q[0] = fmaf(a, a, q[0]); q[1] = fmaf(b, b, q[1]);
                    }
                }
                float s0 = s[0] + s[1], q0 = q[0] + q[1];
#pragma unroll
                for (int o = 1; o <= 2; o <<= 1) { s0 += __shfl_xor_sync(~0u, s0, o); q0 += __shfl_xor_sync(~0u, q0, o); }
                if ((j & 3) == 0) {
                    const float d = s0 * (1.0f / DM);
                    const uint32_t ms = pack2(p0 + d, sqrt_apx(rbf(rbf(fmaxf(fmaf(-d, d, q0 * (1.0f / DM)), 0.f)) + 1e-5f)));
                    asm volatile("st.global.cg.u64 [%0], %1;" ::"l"(g_rstat + mb * 128 + hg * 16 + (j >> 2)), "l"(tagw(ms, tag)) : "memory");
                    g_piv[mb * 128 + hg * 16 + (j >> 2)] = __ushort_as_bfloat16((unsigned short)ms);
                }
            }
            if (layer == 0) {
                ulonglong2 v;
#pragma unroll 1
                for (int it = 0; it < SPIN_MAX; it++) {
                    v = ld_tag2(reinterpret_cast<const ulonglong2*>(g_rstat + mb * 128) + j);
                    if (tag_ok(v, tag)) break;
                    __nanosleep(100);
                }
                *reinterpret_cast<float4*>(rst + 2 * j) = make_float4(__uint_as_float((uint32_t)v.x << 16), rcp_apx(__uint_as_float((uint32_t)v.x & 0xffff0000u)),
                                                                      __uint_as_float((uint32_t)v.y << 16), rcp_apx(__uint_as_float((uint32_t)v.y & 0xffff0000u)));
            } else {
                const int ch = j & 7, kg = (j >> 3) & 3;
                const unsigned char* src = stg + (j >> 5) * 8192 + (hg & 3) * 2048;
                uint4 v[20], pv;
#pragma unroll
                for (int it = 0; it < 5; it++) {
                    mbar_wait(bars + 8 * (it % A1_NST), it / A1_NST);
#pragma unroll
                    for (int k = 0; k < 4; k++) v[4 * it + k] = *reinterpret_cast<const uint4*>(src + (it % A1_NST) * A1_STAGE + (4 * k + kg) * 128 + ((ch ^ ((4 * k + kg) & 7)) << 4));
                    if (it == 0) pv = *reinterpret_cast<const uint4*>(src + (ch << 4));
                    asm volatile("" :: "r"(v[4 * it].x), "r"(v[4 * it + 1].x), "r"(v[4 * it + 2].x), "r"(v[4 * it + 3].x), "r"(pv.x) : "memory");
                    __syncwarp();
                    if ((tid & 31) == 0) mbar_arrive(bar_rd + 8 * it);
                }
                float s[8], q[8], p0[8] = {__uint_as_float(pv.x << 16), __uint_as_float(pv.x & 0xffff0000u), __uint_as_float(pv.y << 16), __uint_as_float(pv.y & 0xffff0000u),
                                           __uint_as_float(pv.z << 16), __uint_as_float(pv.z & 0xffff0000u), __uint_as_float(pv.w << 16), __uint_as_float(pv.w & 0xffff0000u)};
#pragma unroll
                for (int i = 0; i < 8; i++) { s[i] = 0.f; q[i] = 0.f; }
#pragma unroll
                for (int k = 0; k < 20; k++) {
                    const uint32_t w[4] = {v[k].x, v[k].y, v[k].z, v[k].w};
#pragma unroll
                    for (int i = 0; i < 4; i++) {
                        const float a = __uint_as_float(w[i] << 16) - p0[2 * i], b = __uint_as_float(w[i] & 0xffff0000u) - p0[2 * i + 1];
                        s[2 * i] += a; s[2 * i + 1] += b; q[2 * i] = fmaf(a, a, q[2 * i]); q[2 * i + 1] = fmaf(b, b, q[2 * i + 1]);
                    }
                }
#pragma unroll
                for (int i = 0; i < 4; i++) {
                    const bool up = kg & 2;
                    const float ss = __shfl_xor_sync(~0u, up ? s[i] : s[i + 4], 16), qq = __shfl_xor_sync(~0u, up ? q[i] : q[i + 4], 16);
                    s[i] = (up ? s[i + 4] : s[i]) + ss; q[i] = (up ? q[i + 4] : q[i]) + qq; p0[i] = up ? p0[i + 4] : p0[i];
                }
#pragma unroll
                for (int i = 0; i < 2; i++) {
                    const bool up = kg & 1;
                    const float ss = __shfl_xor_sync(~0u, up ? s[i] : s[i + 2], 8), qq = __shfl_xor_sync(~0u, up ? q[i] : q[i + 2], 8);
                    s[i] = (up ? s[i + 2] : s[i]) + ss; q[i] = (up ? q[i + 2] : q[i]) + qq; p0[i] = up ? p0[i + 2] : p0[i];
                }
#pragma unroll
                for (int r = 0; r < 2; r++) {
                    const float d = s[r] * (1.0f / 80.0f);
                    st_tag2(g_part + (mb * 8 + hg) * 128 + 64 * r + j, __float_as_uint(p0[r] + d), __float_as_uint(fmaxf(fmaf(-d, s[r], q[r]), 0.f)), tag);
                }
                const ulonglong2* gp = g_part + mb * 8 * 128 + j;
#pragma unroll 1
                for (int it = 0; it < SPIN_MAX; it++) {
                    if (__all_sync(~0u, tag_ok(ld_tag2(gp + (j & 7) * 128 + 64), tag))) break;
                    __nanosleep(200);
                }
                ulonglong2 pw[16];
#pragma unroll 1
                for (int it = 0; it < SPIN_MAX; it++) {
                    bool ok = true;
#pragma unroll
                    for (int k = 0; k < 16; k++) pw[k] = ld_tag2(gp + k * 64);
#pragma unroll
                    for (int k = 0; k < 16; k++) ok = ok && tag_ok(pw[k], tag);
                    if (ok) break;
                    __nanosleep(200);
                }
                float o[4];
#pragma unroll
                for (int r = 0; r < 2; r++) {
                    float mean = 0.f, m2 = 0.f;
#pragma unroll
                    for (int k = 0; k < 8; k++) mean += __uint_as_float((uint32_t)pw[2 * k + r].x);
                    mean *= 0.125f;
#pragma unroll
                    for (int k = 0; k < 8; k++) {
                        const float dm = __uint_as_float((uint32_t)pw[2 * k + r].x) - mean;
                        m2 += fmaf(80.0f * dm, dm, __uint_as_float((uint32_t)pw[2 * k + r].y));
                    }
                    o[2 * r] = rbf(mean);
                    o[2 * r + 1] = rcp_apx(rbf(sqrt_apx(rbf(rbf(m2 * (1.0f / DM)) + 1e-5f))));
                }
                const int row = (j >> 5) * 64 + (j & 7) * 8 + ((j >> 3) & 3) * 2;
                *reinterpret_cast<float4*>(rst + row) = make_float4(o[0], o[1], o[2], o[3]);
                if (hg == 0) *reinterpret_cast<uint32_t*>(g_piv + SEQ + mb * 128 + row) = __byte_perm(__float_as_uint(o[0]), __float_as_uint(o[2]), 0x7632);
            }
            TSTAMP1T(7, 320);
            __syncwarp();
            if ((tid & 31) == 0) mbar_arrive(bar_stat);
        }
    } else {
        float acc[120];
#pragma unroll
        for (int i = 0; i < 120; i++) acc[i] = 0.f;
        const int lane = tid & 31, warp = w & 7, g = lane >> 2, t = lane & 3;
        if (on) {
            pdl_sync();
            SPAN(1 + 4 * layer, 1);
            TSTAMP1(0);
            if (threadIdx.x == 0) { GSTAMP(g_tim1, 15); }
            TSTAMP3(0);
            if (layer == 0) a1_mainloop<0>(acc, sbase, bars, wg, tile); else a1_mainloop<1>(acc, sbase, bars, wg, tile);
            mbar_wait(bar_stat, 0);
            mbar_wait(bars + 8 * (A1_NST + 3), 1);
            wgmma_wait<0>();
        }
        const float2 sa_ = rst[16 * warp + g], sb_ = rst[16 * warp + g + 8];
        TSTAMP1(2);
        TSTAMP1T(13, 224);
        uint32_t f[30][2];
        auto norm = [&](int j0) {
            float2 cc[10];
#pragma unroll
            for (int j = 0; j < 10; j++) cc[j] = *reinterpret_cast<const float2*>(cs + 8 * (j0 + j) + 2 * t);
#pragma unroll
            for (int j = 0; j < 10; j++) {
                const float* a = acc + 4 * (j0 + j);
                f[j0 + j][0] = pack2(fmaf(-sa_.x, cc[j].x, a[0]) * sa_.y, fmaf(-sa_.x, cc[j].y, a[1]) * sa_.y);
                f[j0 + j][1] = pack2(fmaf(-sb_.x, cc[j].x, a[2]) * sb_.y, fmaf(-sb_.x, cc[j].y, a[3]) * sb_.y);
            }
        };
        norm(10); norm(20);
        if (warp == 7) {
            uint4* hout = g_halo + ((layer * 16 + mb) * 8 + hg) * 320 + lane;
#pragma unroll
            for (int j = 0; j < 20; j += 2)
                asm volatile("st.relaxed.gpu.global.v4.u32 [%0], {%1,%2,%3,%4};" ::"l"(hout + 16 * j), "r"(f[10 + j][0]), "r"(f[10 + j][1]), "r"(f[11 + j][0]), "r"(f[11 + j][1]) : "memory");
        }
        TSTAMP1T(12, 224);
        const uint32_t kvw = sbase + A1_SM_KV + 16 * warp * A1_KVP;
        const uint32_t mrow = kvw + (lane & 15) * A1_KVP + (lane >> 4) * 16;
#pragma unroll
        for (int j = 0; j < 20; j += 2) stsm_x4(mrow + 16 * A1_KVP + 16 * j, f[10 + j][0], f[10 + j][1], f[11 + j][0], f[11 + j][1]);
        __syncwarp();
        if (lane == 0 && on) mbar_arrive(bar_kv + 8 * (warp + 1));
        norm(0);
        TSTAMP1T(10, 64);
        float sc[4][4][4];
        uint32_t qs[4][2];
#pragma unroll
        for (int h = 0; h < 4; h++) {
            const int jb = 5 * (h >> 1) + 3 * (h & 1), js = 5 * (h >> 1) + 2;
            qs[h][0] = (t >> 1) == (h & 1) ? f[js][0] : 0u; qs[h][1] = (t >> 1) == (h & 1) ? f[js][1] : 0u;
#pragma unroll
            for (int nt = 2; nt < 4; nt++) {
#pragma unroll
                for (int e = 0; e < 4; e++) sc[h][nt][e] = 0.f;
                mma_bf16(sc[h][nt], f[jb][0], f[jb][1], f[jb + 1][0], f[jb + 1][1], f[10 + jb][nt - 2], f[11 + jb][nt - 2]);
                mma_bf16_k8(sc[h][nt], qs[h][0], qs[h][1], f[10 + js][nt - 2]);
            }
        }
        if (on) mbar_wait(bar_kv + 8 * warp, 0);
        TSTAMP1(8);
        uint32_t kp[10][2];
#pragma unroll
        for (int j = 0; j < 10; j += 2) ldsm_x4(&kp[j][0], mrow + 16 * j);
#pragma unroll
        for (int h = 0; h < 4; h++) {
            const int jb = 5 * (h >> 1) + 3 * (h & 1), js = 5 * (h >> 1) + 2;
#pragma unroll
            for (int nt = 0; nt < 2; nt++) {
#pragma unroll
                for (int e = 0; e < 4; e++) sc[h][nt][e] = 0.f;
                mma_bf16(sc[h][nt], f[jb][0], f[jb][1], f[jb + 1][0], f[jb + 1][1], kp[jb][nt], kp[jb + 1][nt]);
                mma_bf16_k8(sc[h][nt], qs[h][0], qs[h][1], kp[js][nt]);
            }
        }
        uint32_t vb[10][4];
#pragma unroll
        for (int j = 0; j < 10; j++) ldsm_x4_t(vb[j], kvw + lane * A1_KVP + 160 + 16 * j);
        TSTAMP1T(3, 64);
        const bool odd = g & 1, hi = t > (g >> 1), edge = (mb | warp) == 0;
        float p[4][4], mx[4][2], sum[4][2];
#pragma unroll
        for (int h = 0; h < 4; h++) {
#pragma unroll
            for (int r = 0; r < 2; r++) {
                const float a = odd ? sc[h][1 + r][2 * r + 1] : sc[h][1 + r][2 * r];
                const float b0 = odd ? sc[h][r][2 * r + 1] : sc[h][r][2 * r], b1 = odd ? sc[h][2 + r][2 * r + 1] : sc[h][2 + r][2 * r];
                const uint32_t w1 = pack2(a, hi ? b0 : b1);
                const uint32_t w2 = pack2(__uint_as_float(w1 << 16) * 0.22360679774997896f, __uint_as_float(w1 & 0xffff0000u) * 0.22360679774997896f);
                p[h][2 * r] = __uint_as_float(w2 << 16); p[h][2 * r + 1] = __uint_as_float(w2 & 0xffff0000u);
            }
            if (edge) {
                p[h][0] = -1.0e9f;
                if (hi) { p[h][1] = -1.0e9f; p[h][3] = -1.0e9f; }
            }
            mx[h][0] = fmaxf(p[h][0], p[h][1]); mx[h][1] = fmaxf(p[h][2], p[h][3]);
        }
#pragma unroll
        for (int o = 1; o <= 2; o <<= 1)
#pragma unroll
            for (int h = 0; h < 4; h++)
#pragma unroll
                for (int r = 0; r < 2; r++) mx[h][r] = fmaxf(mx[h][r], __shfl_xor_sync(~0u, mx[h][r], o));
#pragma unroll
        for (int h = 0; h < 4; h++)
#pragma unroll
            for (int r = 0; r < 2; r++) {
                p[h][2 * r] = __expf(p[h][2 * r] - mx[h][r]); p[h][2 * r + 1] = __expf(p[h][2 * r + 1] - mx[h][r]);
                sum[h][r] = p[h][2 * r] + p[h][2 * r + 1];
            }
#pragma unroll
        for (int o = 1; o <= 2; o <<= 1)
#pragma unroll
            for (int h = 0; h < 4; h++)
#pragma unroll
                for (int r = 0; r < 2; r++) sum[h][r] += __shfl_xor_sync(~0u, sum[h][r], o);
        TSTAMP1T(5, 64);
        const uint32_t selA = odd ? 0x1044u : 0x4410u, selB = odd ? 0x3244u : 0x4432u, selH = hi ? selB : 0x4444u, selL = hi ? 0x4444u : selB;
        const uint32_t orow = sbase + A1_SM_O + (16 * warp + (lane & 15)) * 160 + (lane >> 4) * 16;
        uint32_t ob[10][2];
#pragma unroll
        for (int P = 0; P < 2; P++) {
            float os[2][4];
#pragma unroll
            for (int e = 0; e < 2; e++) {
                const int h = 2 * P + e;
                const float i0 = rcp_apx(sum[h][0]), i1 = rcp_apx(sum[h][1]);
                const uint32_t w0 = pack2(p[h][0] * i0, p[h][1] * i0), w1 = pack2(p[h][2] * i1, p[h][3] * i1);
                const uint32_t a00 = __byte_perm(w0, 0, selH), a02 = __byte_perm(w0, 0, selA), a03 = __byte_perm(w1, 0, selH);
                const uint32_t a10 = __byte_perm(w0, 0, selL), a11 = __byte_perm(w1, 0, selA), a13 = __byte_perm(w1, 0, selL);
#pragma unroll
                for (int dt = 0; dt < 3; dt++) {
                    const int j = 5 * P + (dt < 2 ? 3 * e + dt : 2);
                    float o[4] = {0.f, 0.f, 0.f, 0.f};
                    mma_bf16(o, a00, 0u, a02, a03, vb[j][0], vb[j][1]);
                    mma_bf16(o, a10, a11, 0u, a13, vb[j][2], vb[j][3]);
                    if (dt < 2) { ob[j][0] = pack2(o[0], o[1]); ob[j][1] = pack2(o[2], o[3]); }
                    else { os[e][0] = o[0]; os[e][1] = o[1]; os[e][2] = o[2]; os[e][3] = o[3]; }
                }
            }
            ob[5 * P + 2][0] = t < 2 ? pack2(os[0][0], os[0][1]) : pack2(os[1][0], os[1][1]);
            ob[5 * P + 2][1] = t < 2 ? pack2(os[0][2], os[0][3]) : pack2(os[1][2], os[1][3]);
        }
#pragma unroll
        for (int j = 0; j < 10; j += 2) stsm_x4(orow + 16 * j, ob[j][0], ob[j][1], ob[j + 1][0], ob[j + 1][1]);
        fence_async_smem();
        __syncwarp();
        if (on) {
            if (lane == 0) tma_store_2d(&tmOst, hg * 80, mb * 128 + 16 * warp, sbase + A1_SM_O + 16 * warp * 160);
            TSTAMP1T(4, 64);
            TSTAMP1(1);
            GSTAMP(g_tim1, 14);
            SPAN(1 + 4 * layer, 3);
            return;
        }
    }
    mbar_wait(bars + 144, 0);
    mbar_wait(bars + 8 * (A1_NST + 3), 1);
    const uint4* hin = g_halo + ((layer * 16 + mb - 1) * 8 + hg) * 320 + tid - 256;
    uint32_t hv[3][4] = {};
    if (mb > 0) {
#pragma unroll 1
        for (int it = 0; it < SPIN_MAX; it++) {
            bool ok = true;
#pragma unroll
            for (int k = 0; k < 3; k++)
                if (k < 2 || w < 10)
                    asm volatile("ld.relaxed.gpu.global.v4.u32 {%0,%1,%2,%3}, [%4];" : "=r"(hv[k][0]), "=r"(hv[k][1]), "=r"(hv[k][2]), "=r"(hv[k][3]) : "l"(hin + 128 * k) : "memory");
#pragma unroll
            for (int k = 0; k < 3; k++) ok = ok && hv[k][0] != ~0u && hv[k][1] != ~0u && hv[k][2] != ~0u && hv[k][3] != ~0u;
            if (ok) break;
        }
    }
    __syncwarp();
    TSTAMP1T(11, 256);
    const uint32_t hd = sbase + A1_SM_KV + (tid & 15) * A1_KVP + ((tid >> 4) & 1) * 16 + (w - 8) * 32;
#pragma unroll
    for (int k = 0; k < 3; k++)
        if (k < 2 || w < 10) stsm_x4(hd + 128 * k, hv[k][0], hv[k][1], hv[k][2], hv[k][3]);
    __syncwarp();
    if ((tid & 31) == 0) mbar_arrive(bar_kv);
}

constexpr int A2_THREADS = 288;
constexpr int A2_NA = 6;
#define A2_WPRE 4
#define A2_WLEAD 2
#define A2_RPOS 7
constexpr int A2_SM_A = 10 * WO_STAGE;
constexpr int A2_SM_R = A2_SM_A + A2_NA * 16384;
constexpr int A2_SM_BAR = A2_SM_R + 20480;
constexpr int A2_SMEM = A2_SM_BAR + 256 + 1024;

__global__ void __launch_bounds__(A2_THREADS, 1) a2_kernel(const int layer, const __grid_constant__ CUtensorMap tmO, const __grid_constant__ CUtensorMap tmR,
                                                           const __grid_constant__ CUtensorMap tmX1) {
    extern __shared__ unsigned char smraw[];
    const uint32_t sbase = (smem_u32(smraw) + 1023) & ~1023u;
    const uint32_t bars = sbase + A2_SM_BAR, bar_e = bars + 80, bar_r = bars + 128;
    const int tid = threadIdx.x, w = __shfl_sync(~0u, tid >> 5, 0), wg = w >> 2;
    const int tile = sm_tile();
    if (tile >= 128) { sm_idle(2 * layer + 1); return; }
    const int mb = tile >> 3, cg = tile & 7;
    if (wg == 2) {
        const unsigned char* wsrc = reinterpret_cast<const unsigned char*>(g_wo) + cg * 10 * WO_STAGE;
        if (tid == 256) {
            prefetch_tmap(&tmO);
#pragma unroll
            for (int i = 0; i < 17; i++) mbar_init(bars + 8 * i, i >= 10 && i < 16 ? 2 : 1);
            asm volatile("fence.mbarrier_init.release.cluster;" ::: "memory");
#pragma unroll
            for (int kb = 0; kb < A2_WPRE; kb += 2) {
                mbar_expect_tx(bars + 8 * kb, 16384 + 2 * WO_STAGE);
                bulk_load(sbase + kb * WO_STAGE, wsrc + kb * WO_STAGE, 2 * WO_STAGE, bars + 8 * kb);
            }
        }
        __syncwarp();
        asm volatile("bar.arrive 0, 288;" ::: "memory");
        if (tid == 256) {
#pragma unroll
            for (int kb = 0; kb < 10; kb++) if ((kb & 1) || kb >= A2_WPRE) mbar_expect_tx(bars + 8 * kb, (kb & 1) ? 16384 : 16384 + 2 * WO_STAGE);
            mbar_expect_tx(bar_r, 20480);
            pdl_sync();
#pragma unroll 1
            for (int kb = 0; kb < 10; kb++) {
                if (kb >= A2_NA) mbar_wait(bar_e + 8 * (kb - A2_NA), 0);
                tma_load_2d(sbase + A2_SM_A + (kb < A2_NA ? kb : kb - A2_NA) * 16384, &tmO, kb * 64, mb * 128, bars + 8 * kb);
                const int kw = kb + A2_WLEAD;
                if (!(kw & 1) && kw >= A2_WPRE && kw < 10) bulk_load(sbase + kw * WO_STAGE, wsrc + kw * WO_STAGE, 2 * WO_STAGE, bars + 8 * kw);
                if (kb == A2_RPOS) {
                    if (layer == 0) tma_load_2d(sbase + A2_SM_R, &tmR, cg * 80, mb * 128, bar_r);
                    else { tma_load_2d(sbase + A2_SM_R, &tmR, mb * 128, cg * 80, bar_r); tma_load_2d(sbase + A2_SM_R + 10240, &tmR, mb * 128 + 64, cg * 80, bar_r); }
                }
            }
        }
    } else {
        if (tid == 224) { prefetch_tmap(&tmR); prefetch_tmap(&tmX1); sm_started(2 * layer + 1); }
        asm volatile("bar.sync 0, 288;" ::: "memory");
        SPAN(2 + 4 * layer, 0);
        pdl_sync();
        SPAN(2 + 4 * layer, 1);
        TSTAMP2(0);
        TSTAMP4(0);
        if (threadIdx.x == 0) { GSTAMP(g_tim2, 15); }
        const int lane = tid & 31, warp = w, g = lane >> 2, t = lane & 3;
        const int row = layer * SEQ + mb * 128 + 16 * warp + g;
        const unsigned short pv0 = __ldcg(reinterpret_cast<const unsigned short*>(g_piv) + row), pv1 = __ldcg(reinterpret_cast<const unsigned short*>(g_piv) + row + 8);
        float acc[40];
#pragma unroll
        for (int i = 0; i < 40; i++) acc[i] = 0.f;
        const uint64_t da0 = make_desc(sbase + A2_SM_A + wg * 8192, 16, 1024, 1), db0 = make_desc(sbase, 16, 1024, 1);
#pragma unroll 1
        for (int kb = 0; kb < 10; kb++) {
            if (kb == 0) TSTAMP4(11);
            mbar_wait(bars + 8 * kb, 0);
            TSTAMP4(1 + kb);
            wgmma_fence();
#pragma unroll
            for (int kk = 0; kk < 4; kk++) wgmma_n80<0, 0>(acc, da0 + (uint32_t)((kb < A2_NA ? kb : kb - A2_NA) * 1024 + kk * 2), db0 + (uint32_t)(kb * (WO_STAGE / 16) + kk * 2));
            wgmma_commit();
            wgmma_wait<1>();
            if (kb > 0 && kb <= A2_NA && (tid & 127) == 0) mbar_arrive(bar_e + 8 * (kb - 1));
        }
        const uint32_t trow = ((lane & 7) + 8 * (lane >> 4)) * 128 + (((2 * (warp & 3) + ((lane >> 3) & 1)) ^ (lane & 7)) << 4);
        uint32_t xr[10][2];
        mbar_wait(bar_r, 0);
        if (layer == 0) {
#pragma unroll
            for (int j = 0; j < 10; j += 2) ldsm_x4(&xr[j][0], sbase + A2_SM_R + (16 * warp + (lane & 15)) * 160 + (lane >> 4) * 16 + 16 * j);
        } else {
#pragma unroll
            for (int j = 0; j < 10; j += 2) ldsm_x4_t(&xr[j][0], sbase + A2_SM_R + wg * 10240 + trow + 1024 * j);
        }
        mbar_wait(bar_e + 8 * (4 + wg), 0);
        wgmma_wait<0>();
        TSTAMP2(1);
        const float p0 = __uint_as_float((uint32_t)pv0 << 16), p1 = __uint_as_float((uint32_t)pv1 << 16);
        float s[4] = {0.f, 0.f, 0.f, 0.f};
#pragma unroll
        for (int j = 0; j < 10; j++) {
#pragma unroll
            for (int hh = 0; hh < 2; hh++) {
                const uint32_t a = pack2(acc[4 * j + 2 * hh], acc[4 * j + 2 * hh + 1]);
                const __nv_bfloat162 r = __hadd2_rn(*reinterpret_cast<const __nv_bfloat162*>(&xr[j][hh]), *reinterpret_cast<const __nv_bfloat162*>(&a));
                const uint32_t w = *reinterpret_cast<const uint32_t*>(&r);
                xr[j][hh] = w;
                const float d0 = __uint_as_float(w << 16) - (hh ? p1 : p0), d1 = __uint_as_float(w & 0xffff0000u) - (hh ? p1 : p0);
                s[2 * hh] += d0 + d1;
                s[2 * hh + 1] = fmaf(d0, d0, fmaf(d1, d1, s[2 * hh + 1]));
            }
        }
        const uint32_t so = sbase + A2_SM_A + (4 + wg) * 16384;
#pragma unroll
        for (int j = 0; j < 10; j += 2) stsm_x4_t(so + trow + 1024 * j, xr[j][0], xr[j][1], xr[j + 1][0], xr[j + 1][1]);
        fence_async_smem();
        TSTAMP2(2);
#pragma unroll
        for (int o = 1; o <= 2; o <<= 1)
#pragma unroll
            for (int i = 0; i < 4; i++) s[i] += __shfl_xor_sync(~0u, s[i], o);
        if (t < 2) asm volatile("red.relaxed.gpu.global.add.v2.f32 [%0], {%1, %2};" ::"l"(g_sum + layer * SEQ + (g >> 1) * 512 + (mb * 16 + 2 * warp + t) * 2 + (g & 1)), "f"(t ? s[2] : s[0]), "f"(t ? s[3] : s[1]) : "memory");
        if (wg) asm volatile("bar.sync 2, 128;" ::: "memory"); else asm volatile("bar.sync 1, 128;" ::: "memory");
        TSTAMP2(3);
        if ((tid & 127) == 0) tma_store_2d(&tmX1, mb * 128 + 64 * wg, cg * 80, so);
        TSTAMP2(4);
        GSTAMP(g_tim2, 14);
        SPAN(2 + 4 * layer, 3);
    }
}

static int h_nsm;
static void* h_sym[6];
static CUtensorMap h_tmX0, h_tmX1, h_tmOst, h_tmO, h_tmR0, h_tmR1, h_tmX1st, h_tmOut, h_tmWq, h_tmWo;
typedef CUresult (*PFN_encodeTiled)(CUtensorMap*, CUtensorMapDataType, cuuint32_t, void*, const cuuint64_t*, const cuuint64_t*,
                                    const cuuint32_t*, const cuuint32_t*, CUtensorMapInterleave, CUtensorMapSwizzle,
                                    CUtensorMapL2promotion, CUtensorMapFloatOOBfill);
static void make_tmap(CUtensorMap* tm, const void* ptr, uint64_t cols, uint64_t rows, uint32_t bc, uint32_t br, CUtensorMapSwizzle sw, uint64_t pitch = 0) {
    static PFN_encodeTiled fn = nullptr;
    if (!fn) {
        void* p = nullptr; cudaDriverEntryPointQueryResult qr;
        cudaGetDriverEntryPoint("cuTensorMapEncodeTiled", &p, cudaEnableDefault, &qr);
        fn = (PFN_encodeTiled)p;
    }
    if (br == 0) {
        cuuint64_t dims[4] = {cols, 2, rows / 8, 4}; cuuint64_t strides[3] = {cols * 2, cols * 16, cols * 4};
        cuuint32_t box[4] = {bc, 2, 8, 4}; cuuint32_t es[4] = {1, 1, 1, 1};
        fn(tm, CU_TENSOR_MAP_DATA_TYPE_BFLOAT16, 4, const_cast<void*>(ptr), dims, strides, box, es, CU_TENSOR_MAP_INTERLEAVE_NONE, sw,
           CU_TENSOR_MAP_L2_PROMOTION_L2_128B, CU_TENSOR_MAP_FLOAT_OOB_FILL_NONE);
        return;
    }
    cuuint64_t dims[2] = {cols, rows}; cuuint64_t strides[1] = {(pitch ? pitch : cols) * 2};
    cuuint32_t box[2] = {bc, br}; cuuint32_t es[2] = {1, 1};
    fn(tm, CU_TENSOR_MAP_DATA_TYPE_BFLOAT16, 2, const_cast<void*>(ptr), dims, strides, box, es, CU_TENSOR_MAP_INTERLEAVE_NONE, sw,
       CU_TENSOR_MAP_L2_PROMOTION_L2_128B, CU_TENSOR_MAP_FLOAT_OOB_FILL_NONE);
}
template <typename... Args>
static void launch_pdl(void (*kern)(Args...), int grid, int block, int smem, Args... args) {
    cudaLaunchConfig_t cfg = {};
    cfg.gridDim = dim3(grid); cfg.blockDim = dim3(block); cfg.dynamicSmemBytes = smem; cfg.stream = cudaStreamPerThread;
    cudaLaunchAttribute at[1];
    at[0].id = cudaLaunchAttributeProgrammaticStreamSerialization; at[0].val.programmaticStreamSerializationAllowed = 1;
    cfg.attrs = at; cfg.numAttrs = 1;
    cudaLaunchKernelEx(&cfg, kern, args...);
}
static void launch_stage(int k, void* const* d_in, void* d_out) {
    const KgIn kg = {(const bf16*)d_in[4], (const bf16*)d_in[5], (const bf16*)d_in[6], (const bf16*)d_in[7], (const bf16*)d_in[8], (const bf16*)d_in[0], (const bf16*)d_in[1], (const bf16*)d_in[2],
                      (uint4*)h_sym[0], (uint4*)h_sym[1], (uint4*)h_sym[2], (uint4*)h_sym[3], (uint4*)h_sym[4], (float*)h_sym[5]};
    switch (k) {
        case 0: kgen_kernel<<<DM, KG_THREADS, 0, cudaStreamPerThread>>>(kg, h_tmWq, h_tmWo); break;
        case 1: launch_pdl(a1_kernel, h_nsm, A1_THREADS, A1_SMEM, 0, (const bf16*)d_in[0], h_tmX0, h_tmOst); break;
        case 2: launch_pdl(a2_kernel, h_nsm, A2_THREADS, A2_SMEM, 0, h_tmO, h_tmR0, h_tmX1st); break;
        case 3: launch_pdl(conv_kernel, DM / CV_CPB, CV_THREADS, CV_SMEM, (const bf16*)d_in[9], 0, h_tmOut); break;
        case 5: launch_pdl(a1_kernel, h_nsm, A1_THREADS, A1_SMEM, 1, (const bf16*)d_in[0], h_tmX1, h_tmOst); break;
        case 6: launch_pdl(a2_kernel, h_nsm, A2_THREADS, A2_SMEM, 1, h_tmO, h_tmR1, h_tmX1st); break;
        case 7: launch_pdl(conv_kernel, DM / CV_CPB, CV_THREADS, CV_SMEM, (const bf16*)d_in[9], 1, h_tmOut); break;
        default: break;
    }
}
static int n_stage_kernels() { return 9; }
static const char* stage_name(int k) { const char* n[] = {"kgen", "a1", "a2", "conv", "tr", "a1", "a2", "conv", "tr"}; return n[k]; }

extern "C" void kernel_launch(void* const* d_in, const int* in_sizes, int n_in, void* d_out, int out_size) {
    (void)in_sizes; (void)n_in; (void)out_size;
    static const void *p_in = nullptr, *p_w1 = nullptr, *p_w2 = nullptr, *p_out = nullptr;
    if (p_in != d_in[0] || p_w1 != d_in[1] || p_w2 != d_in[2] || p_out != d_out) {
        cudaFuncSetAttribute(conv_kernel, cudaFuncAttributeMaxDynamicSharedMemorySize, CV_SMEM);
        cudaFuncSetAttribute(kgen_kernel, cudaFuncAttributePreferredSharedMemoryCarveout, 100);
        cudaFuncSetAttribute(a1_kernel, cudaFuncAttributeMaxDynamicSharedMemorySize, A1_SMEM);
        cudaFuncSetAttribute(a2_kernel, cudaFuncAttributeMaxDynamicSharedMemorySize, A2_SMEM);
        int dev; cudaGetDevice(&dev); cudaDeviceGetAttribute(&h_nsm, cudaDevAttrMultiProcessorCount, dev);
        if (h_nsm != 132) h_nsm = 128;
        cudaGetSymbolAddress(&h_sym[0], g_tap); cudaGetSymbolAddress(&h_sym[1], g_wq); cudaGetSymbolAddress(&h_sym[2], g_wo);
        cudaGetSymbolAddress(&h_sym[3], g_halo); cudaGetSymbolAddress(&h_sym[4], g_sum); cudaGetSymbolAddress(&h_sym[5], g_csp);
        void *po, *px1, *px2;
        cudaGetSymbolAddress(&po, g_o); cudaGetSymbolAddress(&px1, g_x1T); cudaGetSymbolAddress(&px2, g_xcT);
        make_tmap(&h_tmO, po, 640, 2048, 64, 128, CU_TENSOR_MAP_SWIZZLE_128B);
        make_tmap(&h_tmOst, po, 640, 2048, 80, 16, CU_TENSOR_MAP_SWIZZLE_NONE);
        make_tmap(&h_tmX0, d_in[0], 640, 2048, 64, 128, CU_TENSOR_MAP_SWIZZLE_128B);
        make_tmap(&h_tmX1, px2, 2048, 640, 64, 64, CU_TENSOR_MAP_SWIZZLE_128B, XCP);
        make_tmap(&h_tmR0, d_in[0], 640, 2048, 80, 128, CU_TENSOR_MAP_SWIZZLE_NONE);
        make_tmap(&h_tmR1, px2, 2048, 640, 64, 80, CU_TENSOR_MAP_SWIZZLE_128B, XCP);
        make_tmap(&h_tmX1st, px1, 2048, 640, 64, 80, CU_TENSOR_MAP_SWIZZLE_128B, XCP);
        make_tmap(&h_tmWq, d_in[1], 1920, 640, 32, 0, CU_TENSOR_MAP_SWIZZLE_64B);
        make_tmap(&h_tmWo, d_in[2], 640, 640, 32, 0, CU_TENSOR_MAP_SWIZZLE_64B);
        make_tmap(&h_tmOut, d_out, 640, 2048, 80, 8, CU_TENSOR_MAP_SWIZZLE_NONE);
        p_in = d_in[0]; p_w1 = d_in[1]; p_w2 = d_in[2]; p_out = d_out;
    }
    for (int k = 0; k < n_stage_kernels(); k++) launch_stage(k, d_in, d_out);
}
```

```cpp
#include <cuda_runtime.h>
#include <cuda_bf16.h>
#include <stdint.h>
#include <cuda.h>

typedef __nv_bfloat16 bf16;

constexpr int SEQ = 2048;
constexpr int DM = 640;
constexpr int NMODE = 192;

__device__ __forceinline__ float bf2f(bf16 v) { return __bfloat162float(v); }
__device__ __forceinline__ float rbf(float v) {
    uint32_t r;
    asm("cvt.rn.bf16x2.f32 %0, %1, %2;" : "=r"(r) : "f"(v), "f"(0.f));
    return __uint_as_float(r);
}
__device__ __forceinline__ uint32_t pack2(float lo, float hi) {
    __nv_bfloat162 t = __floats2bfloat162_rn(lo, hi);
    return *reinterpret_cast<uint32_t*>(&t);
}
__device__ __forceinline__ void pdl_sync() {
    asm volatile("griddepcontrol.wait;" ::: "memory");
    asm volatile("griddepcontrol.launch_dependents;" ::: "memory");
}
__device__ __forceinline__ float sqrt_apx(float v) { float r; asm("sqrt.approx.ftz.f32 %0, %1;" : "=f"(r) : "f"(v)); return r; }
__device__ __forceinline__ float rcp_apx(float v) { float r; asm("rcp.approx.ftz.f32 %0, %1;" : "=f"(r) : "f"(v)); return r; }
__device__ __forceinline__ uint32_t smem_u32(const void* p) { return (uint32_t)__cvta_generic_to_shared(p); }

constexpr int TPAD = 16;
constexpr int DLEN = 544;
constexpr int TAP_W2 = DLEN * 8, TAP_W3 = TAP_W2 + 768, TAP_C = TAP_W3 + 768, TAPB = TAP_C + 384;
__device__ __align__(128) uint4 g_tap[DM * 128];
#define XPAD 64
constexpr int XCP = SEQ + XPAD;
__device__ __align__(128) bf16 g_x1T[DM * XCP];
__device__ __align__(128) bf16 g_xcT[DM * XCP];
__device__ __align__(128) bf16 g_o[SEQ * DM];
constexpr int WQ_STAGE = 240 * 128, WO_STAGE = 80 * 128;
__device__ __align__(128) uint4 g_wq[8 * 10 * WQ_STAGE / 16];
__device__ __align__(128) uint4 g_wo[8 * 10 * WO_STAGE / 16];
__device__ __align__(16) float g_csp[10 * 1920];
__device__ __align__(16) float2 g_sum[2 * SEQ];
__device__ __align__(16) bf16 g_piv[2 * SEQ];
__device__ __align__(128) bf16 g_yT[DM * XCP];
__device__ uint32_t g_epoch;
__device__ __align__(16) unsigned long long g_rstat[SEQ];
__device__ ulonglong2 g_part[16 * 8 * 128];
__device__ uint4 g_halo[2 * 128 * 320];
__device__ __forceinline__ unsigned long long tagw(uint32_t payload, uint32_t tag) { return ((unsigned long long)tag << 32) | payload; }
__device__ __forceinline__ void st_tag2(ulonglong2* p, uint32_t a, uint32_t b, uint32_t tag) {
    asm volatile("st.global.cg.v2.u64 [%0], {%1, %2};" ::"l"(p), "l"(tagw(a, tag)), "l"(tagw(b, tag)) : "memory");
}
__device__ __forceinline__ ulonglong2 ld_tag2(const ulonglong2* p) {
    ulonglong2 v;
    asm volatile("ld.relaxed.gpu.global.v2.u64 {%0, %1}, [%2];" : "=l"(v.x), "=l"(v.y) : "l"(p) : "memory");
    return v;
}
__device__ __forceinline__ bool tag_ok(ulonglong2 v, uint32_t tag) { return (uint32_t)(v.x >> 32) == tag && (uint32_t)(v.y >> 32) == tag; }
__device__ __forceinline__ uint32_t ld_epoch() { uint32_t v; asm volatile("ld.relaxed.gpu.global.u32 %0, [%1];" : "=r"(v) : "l"(&g_epoch) : "memory"); return v + 1; }
constexpr int SPIN_MAX = 1 << 20;
__device__ uint32_t g_started[4];
__device__ __forceinline__ void sm_started(int slot) { asm volatile("red.relaxed.gpu.global.add.u32 [%0], 1;" ::"l"(g_started + slot) : "memory"); }
__device__ __noinline__ void sm_idle(int slot) {
    if (threadIdx.x) return;
    sm_started(slot);
    const uint32_t want = ld_epoch() * gridDim.x;
    pdl_sync();
#pragma unroll 1
    for (int it = 0; it < SPIN_MAX; it++) {
        uint32_t v;
        asm volatile("ld.relaxed.gpu.global.u32 %0, [%1];" : "=r"(v) : "l"(g_started + slot) : "memory");
        if ((int)(v - want) >= 0) break;
        __nanosleep(100);
    }
}
__device__ __forceinline__ int sm_tile() {
    uint32_t s;
    asm volatile("mov.u32 %0, %smid;" : "=r"(s));
    const uint32_t h = (s - 64) >> 1, q = (h * 37) >> 8;
    const int t0 = ((s >> 1) & 7) * 16 + (s >> 4) * 2 + (s & 1), t1 = (1 + h - 7 * q) * 16 + 8 + q * 2 + (s & 1), t2 = s - 124 < 8 ? s - 116 : 128;
    return gridDim.x == 128 ? (int)blockIdx.x : s < 64 ? t0 : s < 120 ? t1 : t2;
}
#define DBG_SYMS
#define TSTAMP(i)
#define TSTAMP1(i)
#define TSTAMP1T(i, t)
#define TSTAMP1X(i, t)
#define SPAN(k, i)
#define GSTAMP(arr, i)
#define TSTAMP2(i)
#define TSTAMP3(i)
#define TSTAMP4(i)
#define TSTAMPK(i, t)

__device__ __forceinline__ void mma_bf16(float* d, uint32_t a0, uint32_t a1, uint32_t a2, uint32_t a3, uint32_t b0, uint32_t b1) {
    asm volatile("mma.sync.aligned.m16n8k16.row.col.f32.bf16.bf16.f32 {%0,%1,%2,%3}, {%4,%5,%6,%7}, {%8,%9}, {%0,%1,%2,%3};"
                 : "+f"(d[0]), "+f"(d[1]), "+f"(d[2]), "+f"(d[3]) : "r"(a0), "r"(a1), "r"(a2), "r"(a3), "r"(b0), "r"(b1));
}
__device__ __forceinline__ void mma_bf16_k8(float* d, uint32_t a0, uint32_t a1, uint32_t b0) {
    asm volatile("mma.sync.aligned.m16n8k8.row.col.f32.bf16.bf16.f32 {%0,%1,%2,%3}, {%4,%5}, {%6}, {%0,%1,%2,%3};"
                 : "+f"(d[0]), "+f"(d[1]), "+f"(d[2]), "+f"(d[3]) : "r"(a0), "r"(a1), "r"(b0));
}
__device__ __forceinline__ void ldsm_x4(uint32_t* r, uint32_t addr) {
    asm volatile("ldmatrix.sync.aligned.m8n8.x4.shared.b16 {%0,%1,%2,%3}, [%4];"
                 : "=r"(r[0]), "=r"(r[1]), "=r"(r[2]), "=r"(r[3]) : "r"(addr));
}

__device__ __forceinline__ void ldsm_x4_t(uint32_t* r, uint32_t addr) {
    asm volatile("ldmatrix.sync.aligned.m8n8.x4.trans.shared.b16 {%0,%1,%2,%3}, [%4];"
                 : "=r"(r[0]), "=r"(r[1]), "=r"(r[2]), "=r"(r[3]) : "r"(addr));
}
__device__ __forceinline__ void mbar_init(uint32_t bar, int count) { asm volatile("mbarrier.init.shared::cta.b64 [%0], %1;" ::"r"(bar), "r"(count)); }
__device__ __forceinline__ void mbar_arrive(uint32_t bar) { asm volatile("mbarrier.arrive.shared::cta.b64 _, [%0];" ::"r"(bar) : "memory"); }
__device__ __forceinline__ void mbar_wait(uint32_t bar, uint32_t parity) {
    asm volatile("{\n.reg .pred p;\nWAIT_LOOP:\n"
                 "mbarrier.try_wait.parity.shared::cta.b64 p, [%0], %1;\n"
                 "@p bra.uni WAIT_DONE;\nbra.uni WAIT_LOOP;\nWAIT_DONE:\n}" ::"r"(bar), "r"(parity) : "memory");
}

__device__ __forceinline__ void mbar_expect_tx(uint32_t bar, uint32_t bytes) {
    asm volatile("mbarrier.arrive.expect_tx.shared::cta.b64 _, [%0], %1;" ::"r"(bar), "r"(bytes) : "memory");
}
__device__ __forceinline__ void tma_load_2d(uint32_t dst, const void* tmap, int c0, int c1, uint32_t bar) {
    asm volatile("cp.async.bulk.tensor.2d.shared::cluster.global.mbarrier::complete_tx::bytes [%0], [%1, {%3, %4}], [%2];"
                 ::"r"(dst), "l"(tmap), "r"(bar), "r"(c0), "r"(c1) : "memory");
}
__device__ __forceinline__ void tma_load_3d(uint32_t dst, const void* tmap, int c0, int c1, int c2, uint32_t bar) {
    asm volatile("cp.async.bulk.tensor.3d.shared::cluster.global.mbarrier::complete_tx::bytes [%0], [%1, {%3, %4, %5}], [%2];"
                 ::"r"(dst), "l"(tmap), "r"(bar), "r"(c0), "r"(c1), "r"(c2) : "memory");
}
__device__ __forceinline__ void fence_async_smem() { asm volatile("fence.proxy.async.shared::cta;" ::: "memory"); }
__device__ __forceinline__ void bulk_load(uint32_t dst, const void* src, uint32_t bytes, uint32_t bar) {
    asm volatile("cp.async.bulk.shared::cluster.global.mbarrier::complete_tx::bytes [%0], [%1], %2, [%3];"
                 ::"r"(dst), "l"(src), "r"(bytes), "r"(bar) : "memory");
}
__device__ __forceinline__ void tma_store_2d(const void* tmap, int c0, int c1, uint32_t src) {
    asm volatile("cp.async.bulk.tensor.2d.global.shared::cta.bulk_group [%0, {%1, %2}], [%3];" ::"l"(tmap), "r"(c0), "r"(c1), "r"(src) : "memory");
    asm volatile("cp.async.bulk.commit_group;" ::: "memory");
    asm volatile("cp.async.bulk.wait_group.read 0;" ::: "memory");
}
__device__ __forceinline__ void stsm_x4(uint32_t addr, uint32_t r0, uint32_t r1, uint32_t r2, uint32_t r3) {
    asm volatile("stmatrix.sync.aligned.m8n8.x4.shared.b16 [%0], {%1,%2,%3,%4};" ::"r"(addr), "r"(r0), "r"(r1), "r"(r2), "r"(r3) : "memory");
}
__device__ __forceinline__ void stsm_x4_t(uint32_t addr, uint32_t r0, uint32_t r1, uint32_t r2, uint32_t r3) {
    asm volatile("stmatrix.sync.aligned.m8n8.x4.trans.shared.b16 [%0], {%1,%2,%3,%4};" ::"r"(addr), "r"(r0), "r"(r1), "r"(r2), "r"(r3) : "memory");
}
__device__ __forceinline__ void prefetch_tmap(const void* tmap) { asm volatile("prefetch.tensormap [%0];" ::"l"(tmap) : "memory"); }

__device__ __forceinline__ float2 cexp_at(float wr2, float wi, float p) {
    float er;
    asm("ex2.approx.ftz.f32 %0, %1;" : "=f"(er) : "f"(wr2 * p));
    float th = wi * p;
    const float k = rintf(th * 0.15915494309189535f);
    th = fmaf(k, -6.2831854820251465f, th);
    th = fmaf(k, 1.7484555314695172e-7f, th);
    return make_float2(er * __cosf(th), er * __sinf(th));
}
__device__ __forceinline__ float2 cmul(float2 a, float2 b) {
    return make_float2(fmaf(a.x, b.x, -a.y * b.y), fmaf(a.x, b.y, a.y * b.x));
}
__device__ __forceinline__ float2 csqr(float2 a) { return make_float2(fmaf(a.x, a.x, -a.y * a.y), (a.x + a.x) * a.y); }
__device__ __forceinline__ uint32_t packh(float2 v) {
    uint32_t r;
    asm("cvt.rn.f16x2.f32 %0, %1, %2;" : "=r"(r) : "f"(v.y), "f"(v.x));
    return r;
}
__device__ __forceinline__ void mma_f16(float* d, uint32_t a0, uint32_t a1, uint32_t a2, uint32_t a3, uint32_t b0, uint32_t b1) {
    asm volatile("mma.sync.aligned.m16n8k16.row.col.f32.f16.f16.f32 {%0,%1,%2,%3}, {%4,%5,%6,%7}, {%8,%9}, {%0,%1,%2,%3};"
                 : "+f"(d[0]), "+f"(d[1]), "+f"(d[2]), "+f"(d[3]) : "r"(a0), "r"(a1), "r"(a2), "r"(a3), "r"(b0), "r"(b1));
}

struct KgIn { const bf16 *logA, *Aim, *Cre, *Cim, *logdt, *x, *wqkv, *wo; uint4 *tap, *wq, *wop, *halo, *sum; float* csp; };
constexpr int KG_THREADS = NMODE / 2;

__global__ void __launch_bounds__(KG_THREADS, 5) kgen_kernel(const KgIn in, const __grid_constant__ CUtensorMap tmWq, const __grid_constant__ CUtensorMap tmWo) {
    __shared__ __align__(8) unsigned long long wbar[3];
    __shared__ __align__(1024) uint4 tab[3 * 896];
    const int d = blockIdx.x, tid = threadIdx.x, lane = tid & 31, warp = __shfl_sync(~0u, tid >> 5, 0);
    SPAN(0, 0); SPAN(0, 1);
    TSTAMPK(0, 0);
    asm volatile("griddepcontrol.launch_dependents;" ::: "memory");
    const bf16 pdt = in.logdt[d];
    const uint32_t pla = reinterpret_cast<const uint32_t*>(in.logA)[d * KG_THREADS + tid], pai = reinterpret_cast<const uint32_t*>(in.Aim)[d * KG_THREADS + tid];
    const uint32_t pcr = reinterpret_cast<const uint32_t*>(in.Cre)[d * KG_THREADS + tid], pci = reinterpret_cast<const uint32_t*>(in.Cim)[d * KG_THREADS + tid];
    const bf16* pfq = tid < 30 ? in.wqkv + (size_t)(d * 30 + tid) * 64 : tid < 40 ? in.wo + (size_t)(d * 10 + tid - 30) * 64 : in.x + (size_t)(d * 32 + tid - 40) * 64;
    if (tid < 72) asm volatile("prefetch.global.L2 [%0];" ::"l"(pfq));
    asm volatile("st.global.v4.u32 [%0], {%1,%1,%1,%1};" ::"l"(in.halo + d * 128 + tid), "r"(~0u));
    if (tid < 32) asm volatile("st.global.v4.u32 [%0], {%1,%1,%1,%1};" ::"l"(in.halo + d * 128 + 96 + tid), "r"(~0u));
    const uint32_t tw = smem_u32(tab) + warp * 14336;
    if (lane == 0) { mbar_init(smem_u32(wbar + warp), 1); prefetch_tmap(d >= 200 ? &tmWo : &tmWq); }
    const int g = lane >> 2, t = lane & 3;
    const uint32_t sta = tw + lane * 128 + ((2 * (lane & 3) + ((lane >> 2) & 1)) << 4);
    const uint32_t lda = tw + t * 128 + ((g ^ (2 * t)) << 4);
    const uint32_t stb = tw + 12288 + lane * 64 + ((4 * ((lane >> 1) & 1) + ((lane >> 2) & 3)) << 3);
    const uint32_t ldb = tw + 12288 + t * 64 + ((g ^ (4 * (t >> 1))) << 3);
    auto sts4 = [&](int e, int off, uint32_t a, uint32_t b, uint32_t c, uint32_t dd) {
        asm volatile("st.shared.v4.u32 [%0], {%1,%2,%3,%4};" ::"r"((sta ^ (e << 4)) + off), "r"(a), "r"(b), "r"(c), "r"(dd) : "memory");
    };
    auto lds4 = [&](int sp, int off, uint32_t* r) {
        asm volatile("ld.shared.v4.u32 {%0,%1,%2,%3}, [%4];" : "=r"(r[0]), "=r"(r[1]), "=r"(r[2]), "=r"(r[3]) : "r"((lda ^ ((sp & 1) << 4)) + sp * 512 + off) : "memory");
    };
    const float dt = rbf(expf(bf2f(pdt)));
    float2 C[2], y1[2], z8[2], y128[2];
    float cmax = 0.f;
#pragma unroll
    for (int m = 0; m < 2; m++) {
        const float wr2 = -rbf(expf(__uint_as_float(m ? pla & 0xffff0000u : pla << 16))) * dt * 1.4426950408889634f;
        const float wi = __uint_as_float(m ? pai & 0xffff0000u : pai << 16) * dt;
        C[m] = make_float2(__uint_as_float(m ? pcr & 0xffff0000u : pcr << 16) * dt, -__uint_as_float(m ? pci & 0xffff0000u : pci << 16) * dt);
        cmax = fmaxf(cmax, fmaxf(fabsf(C[m].x), fabsf(C[m].y)));
        y1[m] = cexp_at(wr2, -wi, 1.f); z8[m] = cexp_at(wr2, wi, 8.f); y128[m] = cexp_at(wr2, -wi, 128.f);
    }
    const int ex = min(max((int)(__reduce_max_sync(~0u, __float_as_uint(cmax)) >> 23), 20), 240);
    const float scale = __uint_as_float((uint32_t)(127 + 10 + 127 - ex) << 23), unscale = 2.0f * __uint_as_float((uint32_t)(ex - 10) << 23);
    TSTAMPK(4, 0);
    float k2048 = 0.f;
    float acc[5][4];
#pragma unroll
    for (int j = 0; j < 5; j++)
#pragma unroll
        for (int k = 0; k < 4; k++) acc[j][k] = 0.f;
    uint32_t af[8][4];
    {
        float2 h0[2], h1[2], g0[2], g1[2], g2[2], g2b[2], g3[2], g4[2], y2[2], y4[2];
#pragma unroll
        for (int m = 0; m < 2; m++) {
            h0[m] = make_float2(1.f, 0.f); h1[m] = csqr(csqr(csqr(z8[m])));
            g0[m] = make_float2(C[m].x * scale, C[m].y * scale);
            g1[m] = cmul(g0[m], y128[m]);
            const float2 y256 = csqr(y128[m]), y512 = csqr(y256);
            g2b[m] = g2[m] = cmul(g0[m], y256); g3[m] = cmul(g0[m], y512); g4[m] = cmul(g3[m], y512);
            y2[m] = csqr(y1[m]); y4[m] = csqr(y2[m]);
            const float2 y1024 = csqr(y512);
            k2048 += fmaf(g4[m].x, y1024.x, -g4[m].y * y1024.y);
        }
#pragma unroll
        for (int e = 0; e < 8; e++) {
            sts4(e, 0, packh(h0[0]), packh(h1[0]), packh(h0[1]), packh(h1[1]));
            sts4(e, 4096, packh(g0[0]), packh(g0[1]), packh(g1[0]), packh(g1[1]));
#pragma unroll
            for (int m = 0; m < 2; m++)
                if (e < 7) { h0[m] = e ? cmul(h0[m], z8[m]) : z8[m]; h1[m] = cmul(h1[m], z8[m]); g0[m] = cmul(g0[m], y1[m]); g1[m] = cmul(g1[m], y1[m]); }
            if (e < 5) k2048 += __shfl_xor_sync(~0u, k2048, 1 << e);
        }
        __syncwarp();
#pragma unroll
        for (int e = 0; e < 8; e++) {
            uint32_t b[4];
            lds4(e, 0, af[e]); lds4(e, 4096, b);
            sts4(e, 8192, packh(g2[0]), packh(g2[1]), packh((e & 1) ? cmul(g3[0], y4[0]) : g3[0]), packh((e & 1) ? cmul(g3[1], y4[1]) : g3[1]));
            asm volatile("st.shared.v2.u32 [%0], {%1,%2};" ::"r"(stb ^ (e << 3)), "r"(packh(g4[0])), "r"(packh(g4[1])) : "memory");
#pragma unroll
            for (int m = 0; m < 2; m++)
                if (e < 7) {
                    g2[m] = e == 3 ? cmul(g2b[m], y128[m]) : cmul(g2[m], y2[m]);
                    if (e & 1) g3[m] = cmul(g3[m], y128[m]);
                    g4[m] = cmul(g4[m], y128[m]);
                }
            mma_f16(acc[0], af[e][0], af[e][1], af[e][2], af[e][3], b[0], b[1]);
            mma_f16(acc[1], af[e][0], af[e][1], af[e][2], af[e][3], b[2], b[3]);
        }
    }
    TSTAMPK(6, 0);
    const int job = d * 3 + warp;
    const bool isq = job < 600;
    const int j2 = isq ? job : job - 600, scol = (j2 / 10) * 32, skb = j2 - (j2 / 10) * 10;
    fence_async_smem();
    __syncwarp();
    if (job < 800) {
        if (lane == 0) {
            mbar_expect_tx(smem_u32(wbar + warp), 4096);
            asm volatile("cp.async.bulk.tensor.4d.shared::cluster.global.mbarrier::complete_tx::bytes [%0], [%1, {%3, %4, %5, %4}], [%2];"
                         ::"r"(tw + 4096), "l"(isq ? &tmWq : &tmWo), "r"(smem_u32(wbar + warp)), "r"(scol), "r"(0), "r"(skb * 8) : "memory");
        }
    } else if (job < 800 + 64) in.sum[(job - 800) * 32 + lane] = make_uint4(0, 0, 0, 0);
#pragma unroll
    for (int sp = 0; sp < 8; sp++) {
        uint32_t c[4], e0, e1;
        lds4(sp, 8192, c);
        asm volatile("ld.shared.v2.u32 {%0,%1}, [%2];" : "=r"(e0), "=r"(e1) : "r"((ldb ^ ((sp & 3) << 3)) + sp * 256) : "memory");
        mma_f16(acc[2], af[sp][0], af[sp][1], af[sp][2], af[sp][3], c[0], c[1]);
        mma_f16(acc[3], af[sp][0], af[sp][1], af[sp][2], af[sp][3], c[2], c[3]);
        mma_f16(acc[4], af[sp][0], af[sp][1], af[sp][2], af[sp][3], e0, e1);
    }
    {
        float* Pp = reinterpret_cast<float*>(tab + warp * 896);
#pragma unroll
        for (int h = 0; h < 2; h++) {
            const int b = g + 8 * h;
            *reinterpret_cast<float2*>(Pp + 8 * b + 2 * t) = make_float2(acc[0][2 * h] * unscale, acc[0][2 * h + 1] * unscale);
            *reinterpret_cast<float2*>(Pp + 128 + 8 * b + 2 * t) = make_float2(acc[1][2 * h] * unscale, acc[1][2 * h + 1] * unscale);
            *reinterpret_cast<float2*>(Pp + 256 + 4 * b + 2 * (t & 1) + 64 * (t >> 1)) = make_float2(acc[2][2 * h] * unscale, acc[2][2 * h + 1] * unscale);
            *reinterpret_cast<float2*>(Pp + 384 + 2 * b + 32 * t) = make_float2(acc[3][2 * h] * unscale, acc[3][2 * h + 1] * unscale);
            Pp[512 + b + 32 * t] = acc[4][2 * h] * unscale;
            Pp[512 + b + 32 * t + 16] = acc[4][2 * h + 1] * unscale;
        }
        if (lane == 0) Pp[640] = k2048 * unscale;
    }
    TSTAMPK(7, 0);
    __syncthreads();
    TSTAMPK(9, 0);
    const float* Kp = reinterpret_cast<const float*>(tab);
    auto ksum = [&](int i) -> float { return (Kp[i] + Kp[3584 + i]) + Kp[7168 + i]; };
    auto ksum4 = [&](int q) -> float4 {
        const float4 a = reinterpret_cast<const float4*>(Kp)[q], b = reinterpret_cast<const float4*>(Kp)[896 + q], c = reinterpret_cast<const float4*>(Kp)[1792 + q];
        return make_float4((a.x + b.x) + c.x, (a.y + b.y) + c.y, (a.z + b.z) + c.z, (a.w + b.w) + c.w);
    };
    {
        uint2* E4 = reinterpret_cast<uint2*>(in.tap + d * 128);
        float4 v = ksum4(tid), u = ksum4(96 + min(tid, 64));
        const float cor = rbf(ksum(tid == 95 ? 384 : 512));
        if (tid == 95) v.w -= cor;
        if (tid == 31) u.w -= cor;
        const uint32_t lo = pack2(v.x, v.y), hi = pack2(v.z, v.w);
        if (tid < 64) {
            E4[6 + tid] = make_uint2(lo, hi);
            E4[(tid < 32 ? 159 : 209 - 32) + tid] = make_uint2(pack2(u.x, u.y), pack2(u.z, u.w));
        } else {
            const uint32_t nx = __shfl_down_sync(~0u, lo, 1);
            in.tap[d * 128 + 35 + tid - 64] = make_uint4(__byte_perm(lo, 0, 0x1010), __byte_perm(lo, hi, 0x5432), __byte_perm(hi, 0, 0x1010), __byte_perm(hi, tid == 95 ? 0u : nx, 0x5432));
            if (tid == 64) E4[241] = make_uint2(pack2(u.x, 0.f), 0u);
        }
    }
    TSTAMPK(10, 0);
    if (job < 800) {
        mbar_wait(smem_u32(wbar + warp), 0);
        const uint32_t src = tw + 4096 + ((lane >> 3) * 16 + (lane & 7)) * 64;
#pragma unroll
        for (int cg = 0; cg < 4; cg++) {
            const int col = scol + 8 * cg, sec = col / DM, r = col - sec * DM, hg = r / 80;
            const int n = isq ? hg * 160 + sec * 80 + r : col;
            unsigned char* dst = (isq ? reinterpret_cast<unsigned char*>(in.wq) + (hg * 9 + skb) * WQ_STAGE : reinterpret_cast<unsigned char*>(in.wop) + (hg * 9 + skb) * WO_STAGE) + (n + g) * 128;
            float cs[4] = {0.f, 0.f, 0.f, 0.f};
#pragma unroll
            for (int h = 0; h < 2; h++) {
                uint32_t w[4];
                ldsm_x4_t(w, src + h * 512 + ((cg ^ ((lane >> 1) & 3)) << 4));
                *reinterpret_cast<uint4*>(dst + (((4 * h + t) ^ g) << 4)) = make_uint4(w[0], w[1], w[2], w[3]);
                if (isq) {
                    mma_bf16(cs, 0x3f803f80u, 0u, 0x3f803f80u, 0u, w[0], w[1]);
                    mma_bf16(cs, 0x3f803f80u, 0u, 0x3f803f80u, 0u, w[2], w[3]);
                }
            }
            if (isq && g == cg) *reinterpret_cast<float2*>(in.csp + skb * 1920 + n + 2 * t) = make_float2(cs[0], cs[1]);
        }
    }
    TSTAMPK(11, 0);
    SPAN(0, 3);
}

#define CV_MODE 0
#define CV_SLEEP 100
constexpr int CV_CPB = 5;
constexpr int CV_THREADS = 512;
constexpr int UPADF = 128;
constexpr int ULEN = UPADF + SEQ + 80;
constexpr int XLEN = SEQ + 16;
constexpr int BX_5 = 0, BX_3 = 3264, BX_9 = 6528, BX_7 = 8960, BX_LEN = 11392;
constexpr int CV_SM_T = 0;
constexpr int CV_SM_B = CV_CPB * TAPB;
constexpr int CV_SM_U = CV_SM_B + CV_CPB * BX_LEN;
constexpr int CV_SM_X = CV_SM_U + CV_CPB * ULEN * 2;
constexpr int CV_SM_Y = CV_SM_X + CV_CPB * XLEN * 2;
constexpr int CV_SM_P = CV_SM_Y + CV_CPB * XLEN * 2;
constexpr int CV_SM_CNT = CV_SM_P + 6 * 4096;
constexpr int CV_SM_O = (CV_SM_CNT + 128 + 127) & ~127;
constexpr int CV_SMEM = CV_SM_O + 20480;
static_assert(CV_SM_B % 128 == 0 && CV_SM_CNT % 16 == 0, "layout");

__device__ __forceinline__ uint32_t ln2(uint32_t x, uint32_t m, float ra, float rb) {
    const __nv_bfloat162 d = __hsub2(*reinterpret_cast<const __nv_bfloat162*>(&x), *reinterpret_cast<const __nv_bfloat162*>(&m));
    const uint32_t w = *reinterpret_cast<const uint32_t*>(&d);
    return pack2(__uint_as_float(w << 16) * ra, __uint_as_float(w & 0xffff0000u) * rb);
}
__device__ __forceinline__ void cp_async16(uint32_t dst, const void* src) {
    asm volatile("cp.async.cg.shared.global [%0], [%1], 16;" ::"r"(dst), "l"(src));
}
__device__ __forceinline__ void cp_async_wait_all() { asm volatile("cp.async.wait_all;" ::: "memory"); }

template <bool FULL>
__device__ __forceinline__ void direct_pass(float (&acc)[8][4], uint32_t ub, uint32_t o0, uint32_t o1, const uint2* __restrict__ Tp, bool first_half) {
    uint32_t sw[8][8];
#pragma unroll
    for (int j = 0; j < 8; j++) { ldsm_x4(&sw[j][0], ub + o0 + j * 256); ldsm_x4(&sw[j][4], ub + o1 + j * 256); }
#pragma unroll
    for (int M = 0; M < 4; M++) {
#pragma unroll
        for (int i = 0; i < 4; i++) {
            const uint2 hi = Tp[128 * M + 16 * i], lo = Tp[128 * M + 16 * i - 8];
#pragma unroll
            for (int j = FULL ? 0 : M; j < 8; j++) mma_bf16(acc[j], hi.x, hi.y, lo.x, lo.y, sw[(j - M) & 7][2 * i], sw[(j - M) & 7][2 * i + 1]);
        }
        if (FULL) {
            ldsm_x4(&sw[7 - M][0], ub + o0 - (M + 1) * 256);
            if (M < 3) ldsm_x4(&sw[7 - M][4], ub + o1 - (M + 1) * 256);
        }
    }
    if (first_half) {
        const uint2 hi = Tp[512], lo = Tp[504];
#pragma unroll
        for (int j = FULL ? 0 : 4; j < 8; j++) mma_bf16(acc[j], hi.x, hi.y, lo.x, lo.y, sw[(j - 4) & 7][0], sw[(j - 4) & 7][1]);
    }
}
__device__ __forceinline__ uint32_t fin2(uint32_t x, uint32_t y, uint32_t u, uint32_t dk) {
    typedef __nv_bfloat162 b2;
    const b2 r = __hadd2_rn(*reinterpret_cast<const b2*>(&x), __hadd2_rn(*reinterpret_cast<const b2*>(&y),
                            __hmul2_rn(*reinterpret_cast<const b2*>(&u), *reinterpret_cast<const b2*>(&dk))));
    return *reinterpret_cast<const uint32_t*>(&r);
}
__global__ void __launch_bounds__(CV_THREADS, 1) conv_kernel(const bf16* __restrict__ Dskip, int layer, const __grid_constant__ CUtensorMap tmOut) {
    extern __shared__ __align__(128) unsigned char sm[];
    SPAN(3 + 4 * layer, 0);
    bf16* Us = reinterpret_cast<bf16*>(sm + CV_SM_U);
    bf16* Xs = reinterpret_cast<bf16*>(sm + CV_SM_X);
    bf16* Ys = reinterpret_cast<bf16*>(sm + CV_SM_Y);
    const int tid = threadIdx.x, lane = tid & 31, warp = __shfl_sync(~0u, tid >> 5, 0);
    const int d0 = blockIdx.x * CV_CPB, tile = blockIdx.x; (void)tile;
    const int g = lane >> 2, ti = lane & 3;
    const int e = g - 2 * ti;
    uint32_t lds_off[4];
    uint32_t off2, off3, offc;
    {
        const int mat = lane >> 3, r = lane & 7;
#pragma unroll
        for (int pr = 0; pr < 4; pr++) {
            const int iw = 2 * pr + (mat >> 1), half = mat & 1;
            const int chunk = (UPADF - 16 * iw + 16 * r + 8 * half) >> 3;
            lds_off[pr] = (uint32_t)((chunk ^ ((chunk >> 3) & 1)) * 16);
        }
        const int j2 = 13 + r + 8 * (mat >> 1), j3 = j2 + 2, i0 = 8 * (mat & 1);
        off2 = (j2 & 1) ? BX_3 + (4 * j2 + i0 + 84) * 2 : BX_5 + (4 * j2 + i0 + 80) * 2;
        off3 = ((j3 & 1) ? BX_7 : BX_9) + (8 * j3 + i0 + 136) * 2;
        const int cc = (UPADF + 16 * (r + (mat >> 1)) + i0) >> 3;
        offc = (uint32_t)((cc ^ ((cc >> 3) & 1)) * 16);
    }
    const uint32_t rtab = warp < 8 ? (warp < 4 ? 0x0B090200u : 0x0C0A0301u) : (warp < 12 ? 0x13111008u : 0x1412241Cu);
    const int rl = (rtab >> (8 * (warp & 3))) & 0xff, type = rl >> 3, c = rl & 7;
    const int H = (type == 1 || type == 2) ? 1 : 0, T0 = 8 * H;
    uint32_t toff = CV_SM_T + c * TAPB + (TPAD + e) * 8;
    uint32_t ubase = smem_u32(Us + c * ULEN);
    const uint32_t bbase = smem_u32(sm + CV_SM_B + c * BX_LEN);
    uint32_t rd0, rd1;
    {
        const uint32_t rstart = warp < 8 ? (warp < 4 ? 0x02000000u : 0x06040000u) : (warp < 12 ? 0x0C0B0A08u : 0x1E1D150Fu);
        const uint32_t rcount = warp < 8 ? 0x02020000u : (warp < 12 ? 0x03010102u : 0x01010806u);
        rd0 = (rstart >> (8 * (warp & 3))) & 0xff; rd1 = rd0 + ((rcount >> (8 * (warp & 3))) & 0xff);
    }
    asm volatile("" : "+r"(lds_off[0]), "+r"(lds_off[1]), "+r"(lds_off[2]), "+r"(lds_off[3]), "+r"(ubase), "+r"(toff), "+r"(rd0), "+r"(rd1));
    const uint2* Tc = reinterpret_cast<const uint2*>(sm + toff);
    TSTAMP1X(9, 256);
    unsigned short dskr;
    asm volatile("ld.global.nc.u16 %0, [%1];" : "=h"(dskr) : "l"(Dskip + d0 + min(lane, CV_CPB - 1)));
    if (tid >= 256) {
        const int t2 = tid - 256;
        if (t2 == 0) {
            mbar_init(smem_u32(sm + CV_SM_CNT) + 104, 1);
            asm volatile("fence.mbarrier_init.release.cluster;" ::: "memory");
            mbar_expect_tx(smem_u32(sm + CV_SM_CNT) + 104, CV_CPB * 2048);
            bulk_load(smem_u32(sm + CV_SM_O), g_tap + d0 * 128, CV_CPB * 2048, smem_u32(sm + CV_SM_CNT) + 104);
        } else if (lane == 0) {
            mbar_init(smem_u32(sm + CV_SM_CNT) + 16 * (warp - 9), warp == 15 ? 16 : 1);
            if (warp < 15) mbar_init(smem_u32(sm + CV_SM_CNT) + 16 * (warp - 9) + 8, 1);
            else if (layer) prefetch_tmap(&tmOut);
        }
        if (t2 < 149) {
            const int k = t2;
            const int off = k < 18 ? BX_5 + 8 * k : k < 37 ? BX_3 + 8 * (k - 18) : k < 69 ? BX_9 + 8 * (k - 37) : k < 101 ? BX_7 + 8 * (k - 69)
                          : k < 133 ? 8 * (k - 101) : (UPADF + SEQ) * 2 + 8 * (k - 133);
#pragma unroll
            for (int c = 0; c < CV_CPB; c++) *reinterpret_cast<uint2*>(sm + (k < 101 ? CV_SM_B + c * BX_LEN : CV_SM_U + c * ULEN * 2) + off) = make_uint2(0, 0);
        }
        asm volatile("bar.sync 1, 256;" ::: "memory");
        TSTAMP1X(10, 256);
        mbar_wait(smem_u32(sm + CV_SM_CNT) + 104, 0);
        TSTAMP1X(11, 256);
#pragma unroll 1
        for (int r = t2; r < 392; r += 256) {
            const bool dd = r < 272, cc = r >= 368;
            const uint32_t* E2 = reinterpret_cast<const uint32_t*>(sm + CV_SM_O) + (dd ? r + 3 : r < 320 ? 301 + 2 * (r - 272) : cc ? 417 : 401 + 2 * (r - 320));
            const uint32_t* E3 = E2 + (dd ? 4 : cc ? 0 : 1);
            const uint32_t s0 = !cc ? 0x7610u : r == 382 ? 0x1044u : 0x4444u, s1 = !cc ? 0x7610u : r == 378 ? 0x1044u : 0x4444u;
            const uint32_t s2 = !cc ? 0x1032u : r == 381 ? 0x4410u : 0x4444u, s3 = !cc ? 0x1032u : r == 377 ? 0x4410u : 0x4444u;
            uint32_t w[CV_CPB][4];
#pragma unroll
            for (int c = 0; c < CV_CPB; c++) { w[c][0] = E2[512 * c]; w[c][1] = E2[512 * c + 1]; w[c][2] = E3[512 * c]; w[c][3] = E3[512 * c + 1]; }
#pragma unroll
            for (int c = 0; c < CV_CPB; c++) {
                const uint32_t a = __byte_perm(w[c][3], w[c][2], s1), b = __byte_perm(w[c][1], w[c][0], s2);
                *reinterpret_cast<uint4*>(sm + CV_SM_T + c * TAPB + r * 16) =
                    make_uint4(__byte_perm(w[c][1], w[c][0], s0), dd || cc ? a : b, dd || cc ? b : a, __byte_perm(w[c][3], w[c][2], s3));
            }
        }
        TSTAMP1X(12, 256);
        if (layer == 0) {
#pragma unroll
            for (int c = 0; c < CV_CPB; c++) reinterpret_cast<uint4*>(g_yT + (size_t)(d0 + c) * XCP)[t2] = make_uint4(~0u, ~0u, ~0u, ~0u);
        }
        pdl_sync();
        if (layer && blockIdx.x == 0 && t2 == 0) g_epoch = ld_epoch();
    } else {
        const uint4* ppv = reinterpret_cast<const uint4*>(g_piv + layer * SEQ) + tid;
        const float4* psv = reinterpret_cast<const float4*>(g_sum + layer * SEQ) + tid;
        const uint4* pxv = reinterpret_cast<const uint4*>(g_x1T + (size_t)d0 * XCP) + tid;
        asm volatile("" : "+l"(ppv), "+l"(psv), "+l"(pxv));
        pdl_sync();
        SPAN(3 + 4 * layer, 1);
        TSTAMP(0);
        if (threadIdx.x == 0) { GSTAMP(g_tim, 15); }
        float4 sv[4];
#pragma unroll
        for (int k = 0; k < 4; k++) sv[k] = __ldcg(psv + 256 * k);
        const uint4 pv = __ldcg(ppv);
        uint4 xv[CV_CPB];
#pragma unroll
        for (int c = 0; c < CV_CPB; c++) xv[c] = __ldcg(pxv + c * (XCP / 8));
        uint32_t mw[4];
        float rs[8];
#pragma unroll
        for (int k = 0; k < 4; k++) {
            const uint32_t pw = k == 0 ? pv.x : k == 1 ? pv.y : k == 2 ? pv.z : pv.w;
            const float d0_ = sv[k].x * (1.0f / DM), d1_ = sv[k].z * (1.0f / DM);
            mw[k] = pack2(__uint_as_float(pw << 16) + d0_, __uint_as_float(pw & 0xffff0000u) + d1_);
            const uint32_t vr = pack2(fmaxf(fmaf(-d0_, d0_, sv[k].y * (1.0f / DM)), 0.f), fmaxf(fmaf(-d1_, d1_, sv[k].w * (1.0f / DM)), 0.f));
            const uint32_t ve = pack2(__uint_as_float(vr << 16) + 1e-5f, __uint_as_float(vr & 0xffff0000u) + 1e-5f);
            const uint32_t sd = pack2(sqrt_apx(__uint_as_float(ve << 16)), sqrt_apx(__uint_as_float(ve & 0xffff0000u)));
            rs[2 * k] = rcp_apx(__uint_as_float(sd << 16)); rs[2 * k + 1] = rcp_apx(__uint_as_float(sd & 0xffff0000u));
        }
        if (rs[0] != 123.f) TSTAMP(13);
        const int ch = tid + UPADF / 8, pch = ch ^ ((ch >> 3) & 1);
#pragma unroll
        for (int c = 0; c < CV_CPB; c++) {
            *reinterpret_cast<uint4*>(Xs + c * XLEN + tid * 8) = xv[c];
            *reinterpret_cast<uint4*>(Us + c * ULEN + pch * 8) =
                make_uint4(ln2(xv[c].x, mw[0], rs[0], rs[1]), ln2(xv[c].y, mw[1], rs[2], rs[3]), ln2(xv[c].z, mw[2], rs[4], rs[5]), ln2(xv[c].w, mw[3], rs[6], rs[7]));
        }
    }
    __syncthreads();
    TSTAMP(1);
#pragma unroll 1
    for (int rd = rd0; rd < (int)rd1; rd++) {
        const int i = 32 * rd + lane;
        if (i < CV_CPB * 193) {
            const int c = i / 193, chunk = i - c * 193 - 1, ch = chunk + UPADF / 8;
            const bf16* uc = Us + c * ULEN;
            const uint4 o = *reinterpret_cast<const uint4*>(uc + (ch ^ ((ch >> 3) & 1)) * 8);
            const uint2 lo = *reinterpret_cast<const uint2*>(uc + ((ch - 1) ^ (((ch - 1) >> 3) & 1)) * 8 + 4);
            const uint2 hi = *reinterpret_cast<const uint2*>(uc + ((ch + 1) ^ (((ch + 1) >> 3) & 1)) * 8);
            const uint32_t w[8] = {lo.x, lo.y, o.x, o.y, o.z, o.w, hi.x, hi.y};
            float v[16], b[8];
#pragma unroll
            for (int k = 0; k < 8; k++) { v[2 * k] = __uint_as_float(w[k] << 16); v[2 * k + 1] = __uint_as_float(w[k] & 0xffff0000u); }
            unsigned char* bx = sm + CV_SM_B + c * BX_LEN + chunk * 16;
#pragma unroll
            for (int k = 0; k < 8; k++) b[k] = v[k + 4] + (v[k + 3] + v[k + 5]);
            *reinterpret_cast<uint2*>(bx + BX_3 + 168) = make_uint2(pack2(b[0], b[1]), pack2(b[2], b[3]));
            *reinterpret_cast<uint2*>(bx + BX_3 + 176) = make_uint2(pack2(b[4], b[5]), pack2(b[6], b[7]));
#pragma unroll
            for (int k = 0; k < 8; k++) b[k] += v[k + 2] + v[k + 6];
            *reinterpret_cast<uint4*>(bx + BX_5 + 160) = make_uint4(pack2(b[0], b[1]), pack2(b[2], b[3]), pack2(b[4], b[5]), pack2(b[6], b[7]));
            if (chunk < 128) {
#pragma unroll
                for (int k = 0; k < 8; k++) b[k] += v[k + 1] + v[k + 7];
                *reinterpret_cast<uint4*>(bx + BX_7 + 272) = make_uint4(pack2(b[0], b[1]), pack2(b[2], b[3]), pack2(b[4], b[5]), pack2(b[6], b[7]));
#pragma unroll
                for (int k = 0; k < 8; k++) b[k] += v[k] + v[k + 8];
                *reinterpret_cast<uint4*>(bx + BX_9 + 272) = make_uint4(pack2(b[0], b[1]), pack2(b[2], b[3]), pack2(b[4], b[5]), pack2(b[6], b[7]));
            }
        }
    }
    __syncwarp();
    if (lane == 0) mbar_arrive(smem_u32(sm + CV_SM_CNT) + 96);
    TSTAMP(2);
    {
        float acc[8][4];
#pragma unroll
        for (int j = 0; j < 8; j++)
#pragma unroll
            for (int k = 0; k < 4; k++) acc[j][k] = 0.f;
#pragma unroll 1
        for (int pass = (type == 2 || type == 4) ? 1 : 0; pass < ((type == 1 || type == 3) ? 1 : 2); pass++) {
            const uint32_t o0 = pass ? lds_off[2] : lds_off[0], o1 = pass ? lds_off[3] : lds_off[1];
            if (H) direct_pass<true>(acc, ubase + T0 * 256, o0, o1, Tc + 64 * pass, pass == 0);
            else direct_pass<false>(acc, ubase, o0, o1, Tc + 64 * pass, pass == 0);
        }
        TSTAMP(6);
        mbar_wait(smem_u32(sm + CV_SM_CNT) + 96, 0);
        if (type != 1 && type != 4) {
            const uint32_t* w2 = reinterpret_cast<const uint32_t*>(sm + CV_SM_T + c * TAPB + TAP_W2) + (115 - 96) + 4 * g - 2 * ti;
            uint32_t f[10][2];
#pragma unroll
            for (int k = 0; k < 10; k++) { f[k][0] = w2[16 * k]; f[k][1] = w2[16 * k - 8]; }
            const uint32_t ab = bbase + off2 + (2 * T0 + 6) * 128;
            const int kmax = H ? 23 : 8;
            uint32_t a[3][4];
            ldsm_x4_t(a[0], ab);
            ldsm_x4_t(a[1], ab - 128);
#pragma unroll
            for (int kp = 0; kp < 24; kp++) {
                if (kp > kmax) break;
                if (kp < 22) ldsm_x4_t(a[(kp + 2) % 3], ab - min(kp + 2, kmax) * 128);
#pragma unroll
                for (int j = 0; j < 8; j++) {
                    const int ee = 2 * j - 14 + kp;
                    if (ee >= 0 && ee <= 9) mma_bf16(acc[j], a[kp % 3][0], a[kp % 3][1], a[kp % 3][2], a[kp % 3][3], f[ee][0], f[ee][1]);
                }
            }
        }
        TSTAMP(7);
        if (type != 2 && type != 4) {
            const uint32_t* w3 = reinterpret_cast<const uint32_t*>(sm + CV_SM_T + c * TAPB + TAP_W3) + (129 - 96) + 2 * (g - ti);
            uint32_t f[9][2];
#pragma unroll
            for (int k = 0; k < 9; k++) { f[k][0] = w3[16 * k]; f[k][1] = w3[16 * k - 8]; }
            const uint32_t ab = bbase + off3 + (T0 - 2) * 256;
            uint32_t a[3][4];
            ldsm_x4_t(a[0], ab);
            ldsm_x4_t(a[1], ab - H * 256);
#pragma unroll
            for (int kp = 0; kp < 9; kp++) {
                if (kp > T0) break;
                if (kp < 7) ldsm_x4_t(a[(kp + 2) % 3], ab - min(kp + 2, T0) * 256);
#pragma unroll
                for (int j = 0; j < 8; j++) {
                    const int dl = j - 7 + kp;
                    if (dl >= 0 && dl <= 8) mma_bf16(acc[j], a[kp % 3][0], a[kp % 3][1], a[kp % 3][2], a[kp % 3][3], f[dl][0], f[dl][1]);
                }
            }
            const uint2* Dc = reinterpret_cast<const uint2*>(sm + CV_SM_T + c * TAPB + TAP_C) + e;
            const uint2 h63 = Dc[16], h64 = Dc[32], l63 = Dc[8], l64 = Dc[24];
#pragma unroll
            for (int j = 0; j < 8; j++)
                if (j == 7 || H) {
                    uint32_t bq[4];
                    ldsm_x4(bq, ubase + offc + (T0 + j - 8) * 256);
                    mma_bf16(acc[j], h64.x, h64.y, l64.x, l64.y, bq[0], bq[1]);
                    mma_bf16(acc[j], h63.x, h63.y, l63.x, l63.y, bq[2], bq[3]);
                }
        }
        TSTAMP(8);
        const bool hi_half = (type == 2 || type == 4);
        if (type != 0) {
            const int pair = H ? c : 5;
            float4* give = reinterpret_cast<float4*>(sm + CV_SM_P + pair * 4096 + (hi_half ? 2048 : 0)) + lane;
            const float4* take = reinterpret_cast<const float4*>(sm + CV_SM_P + pair * 4096 + (hi_half ? 0 : 2048)) + lane;
            const uint32_t pb = smem_u32(sm + CV_SM_CNT) + pair * 16;
#pragma unroll
            for (int j = 0; j < 4; j++)
                give[32 * j] = hi_half ? make_float4(acc[j][0], acc[j][1], acc[j][2], acc[j][3]) : make_float4(acc[j + 4][0], acc[j + 4][1], acc[j + 4][2], acc[j + 4][3]);
            __syncwarp();
            if (lane == 0) mbar_arrive(pb + (hi_half ? 8 : 0));
            mbar_wait(pb + (hi_half ? 0 : 8), 0);
#pragma unroll
            for (int j = 0; j < 4; j++) {
                const float4 v = take[32 * j];
                acc[j][0] = (hi_half ? acc[j + 4][0] : acc[j][0]) + v.x; acc[j][1] = (hi_half ? acc[j + 4][1] : acc[j][1]) + v.y;
                acc[j][2] = (hi_half ? acc[j + 4][2] : acc[j][2]) + v.z; acc[j][3] = (hi_half ? acc[j + 4][3] : acc[j][3]) + v.w;
            }
        }
        const uint32_t dk = __shfl_sync(~0u, (uint32_t)dskr, c) * 0x10001u;
#pragma unroll 1
        for (int rnd = 0; rnd < (type == 0 ? 2 : 1); rnd++) {
            const int Q = 2 * H + (hi_half ? 1 : rnd);
            if (rnd) {
#pragma unroll
                for (int j = 0; j < 4; j++)
#pragma unroll
                    for (int k = 0; k < 4; k++) acc[j][k] = acc[j + 4][k];
            }
            const uint32_t ya = smem_u32(Ys + c * XLEN) + (128 * (4 * Q + (lane >> 4)) + 16 * (lane & 7) + 8 * ((lane >> 3) & 1)) * 2;
#pragma unroll
            for (int j = 0; j < 4; j += 2)
                asm volatile("stmatrix.sync.aligned.m8n8.x4.trans.shared.b16 [%0], {%1,%2,%3,%4};" ::"r"(ya + j * 256),
                             "r"(pack2(acc[j][0], acc[j][1])), "r"(pack2(acc[j][2], acc[j][3])),
                             "r"(pack2(acc[j + 1][0], acc[j + 1][1])), "r"(pack2(acc[j + 1][2], acc[j + 1][3])) : "memory");
            __syncwarp();
            uint4 yv[2], xv[2], uv[2];
#pragma unroll
            for (int k = 0; k < 2; k++) {
                const int t = 512 * Q + 256 * k + 8 * lane, cu = (t + UPADF) >> 3;
                yv[k] = *reinterpret_cast<const uint4*>(Ys + c * XLEN + t);
                xv[k] = *reinterpret_cast<const uint4*>(Xs + c * XLEN + t);
                uv[k] = *reinterpret_cast<const uint4*>(Us + c * ULEN + (cu ^ ((cu >> 3) & 1)) * 8);
            }
#pragma unroll
            for (int k = 0; k < 2; k++)
                asm volatile("st.relaxed.gpu.global.v4.u32 [%0], {%1,%2,%3,%4};" ::"l"((layer ? g_yT : g_xcT) + (size_t)(d0 + c) * XCP + 512 * Q + 256 * k + 8 * lane),
                             "r"(fin2(xv[k].x, yv[k].x, uv[k].x, dk)), "r"(fin2(xv[k].y, yv[k].y, uv[k].y, dk)), "r"(fin2(xv[k].z, yv[k].z, uv[k].z, dk)), "r"(fin2(xv[k].w, yv[k].w, uv[k].w, dk)) : "memory");
        }
        TSTAMP(4);
        if (layer == 1) {
            const int mb = blockIdx.x >> 3, cg = blockIdx.x & 7;
            const bf16* src = g_yT + (size_t)(cg * 80 + (tid >> 4)) * XCP + mb * 128 + (tid & 15) * 8;
            uint32_t v[3][4];
            __syncthreads();
            TSTAMP(5);
            uint32_t todo = warp < 8 ? 7 : 3;
#pragma unroll 1
            for (int it = 0; it < SPIN_MAX; it++) {
#pragma unroll
                for (int k = 0; k < 3; k++)
                    if (todo >> k & 1)
                        asm volatile("ld.relaxed.gpu.global.v4.u32 {%0,%1,%2,%3}, [%4];" : "=r"(v[k][0]), "=r"(v[k][1]), "=r"(v[k][2]), "=r"(v[k][3]) : "l"(src + k * (32 * XCP)) : "memory");
#pragma unroll
                for (int k = 0; k < 3; k++)
                    if ((todo >> k & 1) && v[k][0] != ~0u && v[k][1] != ~0u && v[k][2] != ~0u && v[k][3] != ~0u) {
                        *reinterpret_cast<uint4*>(sm + (32 * k + (tid >> 4)) * 272 + (tid & 15) * 16) = make_uint4(v[k][0], v[k][1], v[k][2], v[k][3]);
                        todo ^= 1u << k;
                    }
                if (!todo) break;
                __nanosleep(CV_SLEEP);
            }
            __syncthreads();
            uint32_t w[12];
#pragma unroll
            for (int k = 0; k < 3; k++) ldsm_x4(&w[4 * k], smem_u32(sm) + min(32 * k + lane, 79) * 272 + warp * 16);
            const uint32_t ot = smem_u32(sm + CV_SM_O) + warp * 1280, oa = ot + (lane & 7) * 160 + (lane >> 3) * 16;
            stsm_x4_t(oa, w[0], w[1], w[2], w[3]);
            stsm_x4_t(oa + 64, w[4], w[5], w[6], w[7]);
            asm volatile("stmatrix.sync.aligned.m8n8.x2.trans.shared.b16 [%0], {%1,%2};" ::"r"(oa + 128), "r"(w[8]), "r"(w[9]) : "memory");
            fence_async_smem();
            __syncwarp();
            if (lane == 0) tma_store_2d(&tmOut, cg * 80, mb * 128 + 8 * warp, ot);
        }
    }
    TSTAMP(3);
    GSTAMP(g_tim, 14);
    SPAN(3 + 4 * layer, 3);
}

__device__ __forceinline__ void wgmma_fence() { asm volatile("wgmma.fence.sync.aligned;" ::: "memory"); }
__device__ __forceinline__ void wgmma_commit() { asm volatile("wgmma.commit_group.sync.aligned;" ::: "memory"); }
template <int N> __device__ __forceinline__ void wgmma_wait() { asm volatile("wgmma.wait_group.sync.aligned %0;" ::"n"(N) : "memory"); }
__device__ __forceinline__ uint64_t make_desc(uint32_t addr, uint32_t lbo, uint32_t sbo, uint32_t mode) {
    return (uint64_t)((addr & 0x3FFFF) >> 4) | ((uint64_t)(lbo >> 4) << 16) | ((uint64_t)(sbo >> 4) << 32) | ((uint64_t)mode << 62);
}
template <int TA, int TB>
__device__ __forceinline__ void wgmma_n240(float (&d)[120], uint64_t da, uint64_t db, int acc) {
    asm volatile("{\n.reg .pred p;\nsetp.ne.b32 p, %124, 0;\nwgmma.mma_async.sync.aligned.m64n240k16.f32.bf16.bf16 {%0,%1,%2,%3,%4,%5,%6,%7,%8,%9,%10,%11,%12,%13,%14,%15,%16,%17,%18,%19,%20,%21,%22,%23,%24,%25,%26,%27,%28,%29,%30,%31,%32,%33,%34,%35,%36,%37,%38,%39,%40,%41,%42,%43,%44,%45,%46,%47,%48,%49,%50,%51,%52,%53,%54,%55,%56,%57,%58,%59,%60,%61,%62,%63,%64,%65,%66,%67,%68,%69,%70,%71,%72,%73,%74,%75,%76,%77,%78,%79,%80,%81,%82,%83,%84,%85,%86,%87,%88,%89,%90,%91,%92,%93,%94,%95,%96,%97,%98,%99,%100,%101,%102,%103,%104,%105,%106,%107,%108,%109,%110,%111,%112,%113,%114,%115,%116,%117,%118,%119}, %120, %121, p, 1, 1, %122, %123;\n}"
                 : "+f"(d[0]), "+f"(d[1]), "+f"(d[2]), "+f"(d[3]), "+f"(d[4]), "+f"(d[5]), "+f"(d[6]), "+f"(d[7]), "+f"(d[8]), "+f"(d[9]), "+f"(d[10]), "+f"(d[11]), "+f"(d[12]), "+f"(d[13]), "+f"(d[14]), "+f"(d[15]), "+f"(d[16]), "+f"(d[17]), "+f"(d[18]), "+f"(d[19]), "+f"(d[20]), "+f"(d[21]), "+f"(d[22]), "+f"(d[23]), "+f"(d[24]), "+f"(d[25]), "+f"(d[26]), "+f"(d[27]), "+f"(d[28]), "+f"(d[29]), "+f"(d[30]), "+f"(d[31]), "+f"(d[32]), "+f"(d[33]), "+f"(d[34]), "+f"(d[35]), "+f"(d[36]), "+f"(d[37]), "+f"(d[38]), "+f"(d[39]), "+f"(d[40]), "+f"(d[41]), "+f"(d[42]), "+f"(d[43]), "+f"(d[44]), "+f"(d[45]), "+f"(d[46]), "+f"(d[47]), "+f"(d[48]), "+f"(d[49]), "+f"(d[50]), "+f"(d[51]), "+f"(d[52]), "+f"(d[53]), "+f"(d[54]), "+f"(d[55]), "+f"(d[56]), "+f"(d[57]), "+f"(d[58]), "+f"(d[59]), "+f"(d[60]), "+f"(d[61]), "+f"(d[62]), "+f"(d[63]), "+f"(d[64]), "+f"(d[65]), "+f"(d[66]), "+f"(d[67]), "+f"(d[68]), "+f"(d[69]), "+f"(d[70]), "+f"(d[71]), "+f"(d[72]), "+f"(d[73]), "+f"(d[74]), "+f"(d[75]), "+f"(d[76]), "+f"(d[77]), "+f"(d[78]), "+f"(d[79]), "+f"(d[80]), "+f"(d[81]), "+f"(d[82]), "+f"(d[83]), "+f"(d[84]), "+f"(d[85]), "+f"(d[86]), "+f"(d[87]), "+f"(d[88]), "+f"(d[89]), "+f"(d[90]), "+f"(d[91]), "+f"(d[92]), "+f"(d[93]), "+f"(d[94]), "+f"(d[95]), "+f"(d[96]), "+f"(d[97]), "+f"(d[98]), "+f"(d[99]), "+f"(d[100]), "+f"(d[101]), "+f"(d[102]), "+f"(d[103]), "+f"(d[104]), "+f"(d[105]), "+f"(d[106]), "+f"(d[107]), "+f"(d[108]), "+f"(d[109]), "+f"(d[110]), "+f"(d[111]), "+f"(d[112]), "+f"(d[113]), "+f"(d[114]), "+f"(d[115]), "+f"(d[116]), "+f"(d[117]), "+f"(d[118]), "+f"(d[119])
                 : "l"(da), "l"(db), "n"(TA), "n"(TB), "r"(acc));
}

template <int TA, int TB>
__device__ __forceinline__ void wgmma_n80(float (&d)[40], uint64_t da, uint64_t db, int acc) {
    asm volatile("{\n.reg .pred p;\nsetp.ne.b32 p, %44, 0;\nwgmma.mma_async.sync.aligned.m64n80k16.f32.bf16.bf16 {%0,%1,%2,%3,%4,%5,%6,%7,%8,%9,%10,%11,%12,%13,%14,%15,%16,%17,%18,%19,%20,%21,%22,%23,%24,%25,%26,%27,%28,%29,%30,%31,%32,%33,%34,%35,%36,%37,%38,%39}, %40, %41, p, 1, 1, %42, %43;\n}"
                 : "+f"(d[0]), "+f"(d[1]), "+f"(d[2]), "+f"(d[3]), "+f"(d[4]), "+f"(d[5]), "+f"(d[6]), "+f"(d[7]), "+f"(d[8]), "+f"(d[9]), "+f"(d[10]), "+f"(d[11]), "+f"(d[12]), "+f"(d[13]), "+f"(d[14]), "+f"(d[15]), "+f"(d[16]), "+f"(d[17]), "+f"(d[18]), "+f"(d[19]), "+f"(d[20]), "+f"(d[21]), "+f"(d[22]), "+f"(d[23]), "+f"(d[24]), "+f"(d[25]), "+f"(d[26]), "+f"(d[27]), "+f"(d[28]), "+f"(d[29]), "+f"(d[30]), "+f"(d[31]), "+f"(d[32]), "+f"(d[33]), "+f"(d[34]), "+f"(d[35]), "+f"(d[36]), "+f"(d[37]), "+f"(d[38]), "+f"(d[39])
                 : "l"(da), "l"(db), "n"(TA), "n"(TB), "r"(acc));
}

constexpr int A1_THREADS = 384;
constexpr int A1_NST = 4;
#define A1_PRE0 2
#define A1_SKEW 8
#define A1_PRE1 1
constexpr int A1_STAGE = 16384 + WQ_STAGE;
constexpr int A1_KVP = 336;
constexpr int A1_SM_KV = 2 * A1_STAGE;
constexpr int A1_SM_O = A1_SM_KV + 144 * A1_KVP;
constexpr int A1_SM_BAR = A1_NST * A1_STAGE;
constexpr int A1_SM_CS = A1_SM_BAR + 256;
constexpr int A1_SM_RS = A1_SM_CS + 1024;
constexpr int A1_SMEM = A1_SM_RS + 1024 + 1024;
static_assert(A1_SM_O % 128 == 0 && A1_SM_O + 20480 <= A1_SM_BAR, "layout");

template <int L>
__device__ __forceinline__ void a1_mainloop(float (&acc)[120], uint32_t sbase, uint32_t bars, int wg, int tile) {
    constexpr int layer = L; (void)layer;
    const uint64_t da0 = L ? make_desc(sbase + wg * 8192, 8192, 1024, 1) : make_desc(sbase + wg * 8192, 16, 1024, 1), db0 = make_desc(sbase + 16384, 16, 1024, 1);
#pragma unroll 1
    for (int t = 0; t < 10; t++) {
        const int st = t % A1_NST;
        mbar_wait(bars + 8 * st, (t / A1_NST) & 1);
        if (t == A1_SKEW && wg == 0) mbar_wait(bars + 160, 0);
        TSTAMP3(1 + t);
        wgmma_fence();
#pragma unroll
        for (int kk = 0; kk < 4; kk++) wgmma_n240<L, 0>(acc, da0 + (uint32_t)(st * (A1_STAGE / 16) + kk * (L ? 128 : 2)), db0 + (uint32_t)(st * (A1_STAGE / 16) + kk * 2), kk ? 1 : t);
        wgmma_commit();
        if (t == 9 && threadIdx.x == 128) { mbar_arrive(bars + 160); mbar_arrive(bars + 144); }
        if (t == A1_SKEW - 1 && wg == 0) wgmma_wait<0>(); else wgmma_wait<1>();
        if (t > 0 && t < 9 && (threadIdx.x & 127) == 0) {
            if (t != A1_SKEW || wg) mbar_arrive(bars + 8 * (A1_NST + (t - 1) % A1_NST));
            if (t == A1_SKEW - 1 && wg == 0) mbar_arrive(bars + 8 * (A1_NST + t % A1_NST));
        }
    }
}

__global__ void __launch_bounds__(A1_THREADS, 1) a1_kernel(const int layer, const bf16* __restrict__ x0, const unsigned char* __restrict__ wq, const __grid_constant__ CUtensorMap tmX,
                                                           const __grid_constant__ CUtensorMap tmOst) {
    extern __shared__ unsigned char smraw[];
    const uint32_t sbase = (smem_u32(smraw) + 1023) & ~1023u;
    const uint32_t bars = sbase + A1_SM_BAR;
    const uint32_t bar_stat = bars + 64, bar_kv = bars + 72, bar_rd = bars + 168;
    const int tid = threadIdx.x, w = __shfl_sync(~0u, tid >> 5, 0), wg = w >> 2;
    const int tile = sm_tile();
    if (tile >= 128) { sm_idle(2 * layer); return; }
    const int mb = (tile >> 2) & 15, hg = 4 * (tile >> 6) + (tile & 3);
    unsigned char* stg = smraw + (sbase - smem_u32(smraw));
    float* cs = reinterpret_cast<float*>(stg + A1_SM_CS);
    float2* rst = reinterpret_cast<float2*>(stg + A1_SM_RS);
    const int pre = layer ? A1_PRE1 : A1_PRE0;
    auto issue_w = [&](int it) {
        const int kb = it + 5 * (hg >> 2) - (it + 5 * (hg >> 2) >= 10 ? 10 : 0);
        bulk_load(sbase + (it % A1_NST) * A1_STAGE + 16384, wq + (hg * 10 + kb) * WQ_STAGE, WQ_STAGE, bars + 8 * (it % A1_NST));
    };
    auto issue_x = [&](int it) {
        const int kb = it + 5 * (hg >> 2) - (it + 5 * (hg >> 2) >= 10 ? 10 : 0);
        const uint32_t dst = sbase + (it % A1_NST) * A1_STAGE, full = bars + 8 * (it % A1_NST);
        tma_load_3d(dst, &tmX, layer ? 0 : kb * 64, layer ? kb * 64 : 0, mb * 2, full);
    };
    if (w == 8) {
        if (tid == 256) {
            prefetch_tmap(&tmX);
#pragma unroll
            for (int i = 0; i < A1_NST; i++) { mbar_init(bars + 8 * i, 1); mbar_init(bars + 8 * (A1_NST + i), 2); }
            asm volatile("fence.mbarrier_init.release.cluster;" ::: "memory");
#pragma unroll
            for (int i = 0; i < A1_NST; i++) mbar_expect_tx(bars + 8 * i, A1_STAGE);
        }
        __syncwarp();
        asm volatile("bar.arrive 0, 384;" ::: "memory");
        if (tid == 256) {
#pragma unroll 1
            for (int kb = 0; kb < pre; kb++) { if (layer) issue_w(kb); else issue_x(kb); }
            pdl_sync();
#pragma unroll 1
            for (int kb = 0; kb < A1_NST; kb++) {
                if (kb >= pre || layer) issue_x(kb);
                if (kb >= pre || !layer) issue_w(kb);
            }
        }
    } else {
        if (tid == 0) {
            mbar_init(bar_stat, 3);
#pragma unroll
            for (int i = 0; i < 9; i++) mbar_init(bar_kv + 8 * i, i ? 1 : 4);
            mbar_init(bars + 144, 1);
            mbar_init(bars + 160, 1);
#pragma unroll
            for (int i = 0; i < 5; i++) mbar_init(bar_rd + 8 * i, 2);
            asm volatile("fence.mbarrier_init.release.cluster;" ::: "memory");
        } else if (tid == 320) prefetch_tmap(&tmOst);
        asm volatile("bar.sync 0, 384;" ::: "memory");
    }
    SPAN(1 + 4 * layer, 0);
    constexpr int on = 1;
    if (wg == 2) {
        if (w == 9) {
            if (layer == 0) pdl_sync();
            float4 a[2] = {};
#pragma unroll
            for (int k = 0; k < 10; k++)
#pragma unroll
                for (int h = 0; h < 2; h++) {
                    const float4 v = __ldcg(reinterpret_cast<const float4*>(g_csp + k * 1920 + hg * 240) + min(tid - 288 + 32 * h, 59));
                    a[h].x += v.x; a[h].y += v.y; a[h].z += v.z; a[h].w += v.w;
                }
            reinterpret_cast<float4*>(cs)[tid - 288] = a[0];
            reinterpret_cast<float4*>(cs)[min(tid - 256, 59)] = a[1];
            __syncwarp();
            if (tid == 288) mbar_arrive(bar_stat);
        } else if (w == 8) {
            if (tid == 256) {
#pragma unroll 1
                for (int kb = A1_NST; kb < 10; kb++) {
                    mbar_wait(bars + 8 * (A1_NST + kb % A1_NST), ((kb / A1_NST) - 1) & 1);
                    if (layer && kb < 9) mbar_wait(bar_rd + 8 * (kb - A1_NST), 0);
                    mbar_expect_tx(bars + 8 * (kb % A1_NST), A1_STAGE);
                    issue_x(kb); issue_w(kb);
                }
                TSTAMP1T(6, 256);
            }
            __syncwarp();
        } else {
            const int j = tid - 320;
            const uint32_t tag = ld_epoch();
            if (tid == 352) sm_started(2 * layer);
            if (layer == 0) {
                const uint4* src = reinterpret_cast<const uint4*>(x0 + (size_t)(mb * 128 + hg * 16 + (j >> 2)) * DM);
                uint4 v[20];
#pragma unroll
                for (int k = 0; k < 20; k++) v[k] = __ldg(src + (j & 3) + 4 * k);
                const float p0 = __uint_as_float(__shfl_sync(~0u, v[0].x, j & 28) << 16);
                float s[2] = {0.f, 0.f}, q[2] = {0.f, 0.f};
#pragma unroll
                for (int k = 0; k < 20; k++) {
                    const uint32_t w[4] = {v[k].x, v[k].y, v[k].z, v[k].w};
#pragma unroll
                    for (int i = 0; i < 4; i++) {
                        const float a = __uint_as_float(w[i] << 16) - p0, b = __uint_as_float(w[i] & 0xffff0000u) - p0;
                        s[0] += a; s[1] += b; q[0] = fmaf(a, a, q[0]); q[1] = fmaf(b, b, q[1]);
                    }
                }
                float s0 = s[0] + s[1], q0 = q[0] + q[1];
#pragma unroll
                for (int o = 1; o <= 2; o <<= 1) { s0 += __shfl_xor_sync(~0u, s0, o); q0 += __shfl_xor_sync(~0u, q0, o); }
                if ((j & 3) == 0) {
                    const float d = s0 * (1.0f / DM);
                    const uint32_t ms = pack2(p0 + d, sqrt_apx(rbf(rbf(fmaxf(fmaf(-d, d, q0 * (1.0f / DM)), 0.f)) + 1e-5f)));
                    asm volatile("st.global.cg.u64 [%0], %1;" ::"l"(g_rstat + mb * 128 + hg * 16 + (j >> 2)), "l"(tagw(ms, tag)) : "memory");
                    g_piv[mb * 128 + hg * 16 + (j >> 2)] = __ushort_as_bfloat16((unsigned short)ms);
                }
            }
            if (layer == 0) {
                ulonglong2 v;
#pragma unroll 1
                for (int it = 0; it < SPIN_MAX; it++) {
                    v = ld_tag2(reinterpret_cast<const ulonglong2*>(g_rstat + mb * 128) + j);
                    if (tag_ok(v, tag)) break;
                    __nanosleep(100);
                }
                *reinterpret_cast<float4*>(rst + 2 * j) = make_float4(__uint_as_float((uint32_t)v.x << 16), rcp_apx(__uint_as_float((uint32_t)v.x & 0xffff0000u)),
                                                                      __uint_as_float((uint32_t)v.y << 16), rcp_apx(__uint_as_float((uint32_t)v.y & 0xffff0000u)));
            } else {
                const int ch = j & 7, kg = (j >> 3) & 3;
                const unsigned char* src = stg + (j >> 5) * 8192 + (hg & 3) * 2048;
                uint4 v[20], pv;
#pragma unroll
                for (int it = 0; it < 5; it++) {
                    mbar_wait(bars + 8 * (it % A1_NST), it / A1_NST);
#pragma unroll
                    for (int k = 0; k < 4; k++) v[4 * it + k] = *reinterpret_cast<const uint4*>(src + (it % A1_NST) * A1_STAGE + (4 * k + kg) * 128 + ((ch ^ ((4 * k + kg) & 7)) << 4));
                    if (it == 0) pv = *reinterpret_cast<const uint4*>(src + (ch << 4));
                    asm volatile("" :: "r"(v[4 * it].x), "r"(v[4 * it + 1].x), "r"(v[4 * it + 2].x), "r"(v[4 * it + 3].x), "r"(pv.x) : "memory");
                    __syncwarp();
                    if ((tid & 31) == 0) mbar_arrive(bar_rd + 8 * it);
                }
                float s[8], q[8], p0[8] = {__uint_as_float(pv.x << 16), __uint_as_float(pv.x & 0xffff0000u), __uint_as_float(pv.y << 16), __uint_as_float(pv.y & 0xffff0000u),
                                           __uint_as_float(pv.z << 16), __uint_as_float(pv.z & 0xffff0000u), __uint_as_float(pv.w << 16), __uint_as_float(pv.w & 0xffff0000u)};
#pragma unroll
                for (int i = 0; i < 8; i++) { s[i] = 0.f; q[i] = 0.f; }
#pragma unroll
                for (int k = 0; k < 20; k++) {
                    const uint32_t w[4] = {v[k].x, v[k].y, v[k].z, v[k].w};
#pragma unroll
                    for (int i = 0; i < 4; i++) {
                        const float a = __uint_as_float(w[i] << 16) - p0[2 * i], b = __uint_as_float(w[i] & 0xffff0000u) - p0[2 * i + 1];
                        s[2 * i] += a; s[2 * i + 1] += b; q[2 * i] = fmaf(a, a, q[2 * i]); q[2 * i + 1] = fmaf(b, b, q[2 * i + 1]);
                    }
                }
#pragma unroll
                for (int i = 0; i < 4; i++) {
                    const bool up = kg & 2;
                    const float ss = __shfl_xor_sync(~0u, up ? s[i] : s[i + 4], 16), qq = __shfl_xor_sync(~0u, up ? q[i] : q[i + 4], 16);
                    s[i] = (up ? s[i + 4] : s[i]) + ss; q[i] = (up ? q[i + 4] : q[i]) + qq; p0[i] = up ? p0[i + 4] : p0[i];
                }
#pragma unroll
                for (int i = 0; i < 2; i++) {
                    const bool up = kg & 1;
                    const float ss = __shfl_xor_sync(~0u, up ? s[i] : s[i + 2], 8), qq = __shfl_xor_sync(~0u, up ? q[i] : q[i + 2], 8);
                    s[i] = (up ? s[i + 2] : s[i]) + ss; q[i] = (up ? q[i + 2] : q[i]) + qq; p0[i] = up ? p0[i + 2] : p0[i];
                }
#pragma unroll
                for (int r = 0; r < 2; r++) {
                    const float d = s[r] * (1.0f / 80.0f);
                    st_tag2(g_part + (mb * 8 + hg) * 128 + 64 * r + j, __float_as_uint(p0[r] + d), __float_as_uint(fmaxf(fmaf(-d, s[r], q[r]), 0.f)), tag);
                }
                const ulonglong2* gp = g_part + mb * 8 * 128 + j;
#pragma unroll 1
                for (int it = 0; it < SPIN_MAX; it++) {
                    if (__all_sync(~0u, tag_ok(ld_tag2(gp + (j & 7) * 128 + 64), tag))) break;
                    __nanosleep(200);
                }
                ulonglong2 pw[16];
#pragma unroll 1
                for (int it = 0; it < SPIN_MAX; it++) {
                    bool ok = true;
#pragma unroll
                    for (int k = 0; k < 16; k++) pw[k] = ld_tag2(gp + k * 64);
#pragma unroll
                    for (int k = 0; k < 16; k++) ok = ok && tag_ok(pw[k], tag);
                    if (ok) break;
                    __nanosleep(200);
                }
                float o[4];
#pragma unroll
                for (int r = 0; r < 2; r++) {
                    float mean = 0.f, m2 = 0.f;
#pragma unroll
                    for (int k = 0; k < 8; k++) mean += __uint_as_float((uint32_t)pw[2 * k + r].x);
                    mean *= 0.125f;
#pragma unroll
                    for (int k = 0; k < 8; k++) {
                        const float dm = __uint_as_float((uint32_t)pw[2 * k + r].x) - mean;
                        m2 += fmaf(80.0f * dm, dm, __uint_as_float((uint32_t)pw[2 * k + r].y));
                    }
                    o[2 * r] = rbf(mean);
                    o[2 * r + 1] = rcp_apx(rbf(sqrt_apx(rbf(rbf(m2 * (1.0f / DM)) + 1e-5f))));
                }
                const int row = (j >> 5) * 64 + (j & 7) * 8 + ((j >> 3) & 3) * 2;
                *reinterpret_cast<float4*>(rst + row) = make_float4(o[0], o[1], o[2], o[3]);
                if (hg == 0) *reinterpret_cast<uint32_t*>(g_piv + SEQ + mb * 128 + row) = __byte_perm(__float_as_uint(o[0]), __float_as_uint(o[2]), 0x7632);
            }
            TSTAMP1T(7, 320);
            __syncwarp();
            if ((tid & 31) == 0) mbar_arrive(bar_stat);
        }
    } else {
        float acc[120];
        const int lane = tid & 31, warp = w & 7, g = lane >> 2, t = lane & 3;
        if (on) {
            SPAN(1 + 4 * layer, 1);
            TSTAMP1(0);
            if (threadIdx.x == 0) { GSTAMP(g_tim1, 15); }
            TSTAMP3(0);
            if (layer == 0) a1_mainloop<0>(acc, sbase, bars, wg, tile); else a1_mainloop<1>(acc, sbase, bars, wg, tile);
            mbar_wait(bar_stat, 0);
            mbar_wait(bars + 8 * (A1_NST + 3), 1);
            wgmma_wait<0>();
        }
        const float2 sa_ = rst[16 * warp + g], sb_ = rst[16 * warp + g + 8];
        TSTAMP1(2);
        TSTAMP1T(13, 224);
        uint32_t f[30][2];
        auto norm = [&](int j0) {
            float2 cc[10];
#pragma unroll
            for (int j = 0; j < 10; j++) cc[j] = *reinterpret_cast<const float2*>(cs + 8 * (j0 + j) + 2 * t);
#pragma unroll
            for (int j = 0; j < 10; j++) {
                const float* a = acc + 4 * (j0 + j);
                f[j0 + j][0] = pack2(fmaf(-sa_.x, cc[j].x, a[0]) * sa_.y, fmaf(-sa_.x, cc[j].y, a[1]) * sa_.y);
                f[j0 + j][1] = pack2(fmaf(-sb_.x, cc[j].x, a[2]) * sb_.y, fmaf(-sb_.x, cc[j].y, a[3]) * sb_.y);
            }
        };
        norm(10); norm(20);
        if (warp == 7) {
            uint4* hout = g_halo + ((layer * 16 + mb) * 8 + hg) * 320 + lane;
#pragma unroll
            for (int j = 0; j < 20; j += 2)
                asm volatile("st.relaxed.gpu.global.v4.u32 [%0], {%1,%2,%3,%4};" ::"l"(hout + 16 * j), "r"(f[10 + j][0]), "r"(f[10 + j][1]), "r"(f[11 + j][0]), "r"(f[11 + j][1]) : "memory");
        }
        TSTAMP1T(12, 224);
        const uint32_t kvw = sbase + A1_SM_KV + 16 * warp * A1_KVP;
        const uint32_t mrow = kvw + (lane & 15) * A1_KVP + (lane >> 4) * 16;
#pragma unroll
        for (int j = 0; j < 20; j += 2) stsm_x4(mrow + 16 * A1_KVP + 16 * j, f[10 + j][0], f[10 + j][1], f[11 + j][0], f[11 + j][1]);
        __syncwarp();
        if (lane == 0 && on) mbar_arrive(bar_kv + 8 * (warp + 1));
        norm(0);
        TSTAMP1T(10, 64);
        float sc[4][4][4];
        uint32_t qs[4][2];
#pragma unroll
        for (int h = 0; h < 4; h++) {
            const int jb = 5 * (h >> 1) + 3 * (h & 1), js = 5 * (h >> 1) + 2;
            qs[h][0] = (t >> 1) == (h & 1) ? f[js][0] : 0u; qs[h][1] = (t >> 1) == (h & 1) ? f[js][1] : 0u;
#pragma unroll
            for (int nt = 2; nt < 4; nt++) {
#pragma unroll
                for (int e = 0; e < 4; e++) sc[h][nt][e] = 0.f;
                mma_bf16(sc[h][nt], f[jb][0], f[jb][1], f[jb + 1][0], f[jb + 1][1], f[10 + jb][nt - 2], f[11 + jb][nt - 2]);
                mma_bf16_k8(sc[h][nt], qs[h][0], qs[h][1], f[10 + js][nt - 2]);
            }
        }
        if (on) mbar_wait(bar_kv + 8 * warp, 0);
        TSTAMP1(8);
        uint32_t kp[10][2];
#pragma unroll
        for (int j = 0; j < 10; j += 2) ldsm_x4(&kp[j][0], mrow + 16 * j);
#pragma unroll
        for (int h = 0; h < 4; h++) {
            const int jb = 5 * (h >> 1) + 3 * (h & 1), js = 5 * (h >> 1) + 2;
#pragma unroll
            for (int nt = 0; nt < 2; nt++) {
#pragma unroll
                for (int e = 0; e < 4; e++) sc[h][nt][e] = 0.f;
                mma_bf16(sc[h][nt], f[jb][0], f[jb][1], f[jb + 1][0], f[jb + 1][1], kp[jb][nt], kp[jb + 1][nt]);
                mma_bf16_k8(sc[h][nt], qs[h][0], qs[h][1], kp[js][nt]);
            }
        }
        uint32_t vb[10][4];
#pragma unroll
        for (int j = 0; j < 10; j++) ldsm_x4_t(vb[j], kvw + lane * A1_KVP + 160 + 16 * j);
        TSTAMP1T(3, 64);
        const bool odd = g & 1, hi = t > (g >> 1), edge = (mb | warp) == 0;
        float p[4][4], mx[4][2], sum[4][2];
#pragma unroll
        for (int h = 0; h < 4; h++) {
#pragma unroll
            for (int r = 0; r < 2; r++) {
                const float a = odd ? sc[h][1 + r][2 * r + 1] : sc[h][1 + r][2 * r];
                const float b0 = odd ? sc[h][r][2 * r + 1] : sc[h][r][2 * r], b1 = odd ? sc[h][2 + r][2 * r + 1] : sc[h][2 + r][2 * r];
                const uint32_t w1 = pack2(a, hi ? b0 : b1);
                const uint32_t w2 = pack2(__uint_as_float(w1 << 16) * 0.22360679774997896f, __uint_as_float(w1 & 0xffff0000u) * 0.22360679774997896f);
                p[h][2 * r] = __uint_as_float(w2 << 16); p[h][2 * r + 1] = __uint_as_float(w2 & 0xffff0000u);
            }
            if (edge) {
                p[h][0] = -1.0e9f;
                if (hi) { p[h][1] = -1.0e9f; p[h][3] = -1.0e9f; }
            }
            mx[h][0] = fmaxf(p[h][0], p[h][1]); mx[h][1] = fmaxf(p[h][2], p[h][3]);
        }
#pragma unroll
        for (int o = 1; o <= 2; o <<= 1)
#pragma unroll
            for (int h = 0; h < 4; h++)
#pragma unroll
                for (int r = 0; r < 2; r++) mx[h][r] = fmaxf(mx[h][r], __shfl_xor_sync(~0u, mx[h][r], o));
#pragma unroll
        for (int h = 0; h < 4; h++)
#pragma unroll
            for (int r = 0; r < 2; r++) {
                p[h][2 * r] = __expf(p[h][2 * r] - mx[h][r]); p[h][2 * r + 1] = __expf(p[h][2 * r + 1] - mx[h][r]);
                sum[h][r] = p[h][2 * r] + p[h][2 * r + 1];
            }
#pragma unroll
        for (int o = 1; o <= 2; o <<= 1)
#pragma unroll
            for (int h = 0; h < 4; h++)
#pragma unroll
                for (int r = 0; r < 2; r++) sum[h][r] += __shfl_xor_sync(~0u, sum[h][r], o);
        TSTAMP1T(5, 64);
        const uint32_t selA = odd ? 0x1044u : 0x4410u, selB = odd ? 0x3244u : 0x4432u, selH = hi ? selB : 0x4444u, selL = hi ? 0x4444u : selB;
        const uint32_t orow = sbase + A1_SM_O + (16 * warp + (lane & 15)) * 160 + (lane >> 4) * 16;
        uint32_t ob[10][2];
#pragma unroll
        for (int P = 0; P < 2; P++) {
            float os[2][4];
#pragma unroll
            for (int e = 0; e < 2; e++) {
                const int h = 2 * P + e;
                const float i0 = rcp_apx(sum[h][0]), i1 = rcp_apx(sum[h][1]);
                const uint32_t w0 = pack2(p[h][0] * i0, p[h][1] * i0), w1 = pack2(p[h][2] * i1, p[h][3] * i1);
                const uint32_t a00 = __byte_perm(w0, 0, selH), a02 = __byte_perm(w0, 0, selA), a03 = __byte_perm(w1, 0, selH);
                const uint32_t a10 = __byte_perm(w0, 0, selL), a11 = __byte_perm(w1, 0, selA), a13 = __byte_perm(w1, 0, selL);
#pragma unroll
                for (int dt = 0; dt < 3; dt++) {
                    const int j = 5 * P + (dt < 2 ? 3 * e + dt : 2);
                    float o[4] = {0.f, 0.f, 0.f, 0.f};
                    mma_bf16(o, a00, 0u, a02, a03, vb[j][0], vb[j][1]);
                    mma_bf16(o, a10, a11, 0u, a13, vb[j][2], vb[j][3]);
                    if (dt < 2) { ob[j][0] = pack2(o[0], o[1]); ob[j][1] = pack2(o[2], o[3]); }
                    else { os[e][0] = o[0]; os[e][1] = o[1]; os[e][2] = o[2]; os[e][3] = o[3]; }
                }
            }
            ob[5 * P + 2][0] = t < 2 ? pack2(os[0][0], os[0][1]) : pack2(os[1][0], os[1][1]);
            ob[5 * P + 2][1] = t < 2 ? pack2(os[0][2], os[0][3]) : pack2(os[1][2], os[1][3]);
        }
#pragma unroll
        for (int j = 0; j < 10; j += 2) stsm_x4(orow + 16 * j, ob[j][0], ob[j][1], ob[j + 1][0], ob[j + 1][1]);
        fence_async_smem();
        __syncwarp();
        if (on) {
            if (lane == 0) tma_store_2d(&tmOst, hg * 80, mb * 128 + 16 * warp, sbase + A1_SM_O + 16 * warp * 160);
            TSTAMP1T(4, 64);
            TSTAMP1(1);
            GSTAMP(g_tim1, 14);
            SPAN(1 + 4 * layer, 3);
            return;
        }
    }
    mbar_wait(bars + 144, 0);
    mbar_wait(bars + 8 * (A1_NST + 3), 1);
    const uint4* hin = g_halo + ((layer * 16 + mb - 1) * 8 + hg) * 320 + tid - 256;
    uint32_t hv[3][4] = {};
    if (mb > 0) {
#pragma unroll 1
        for (int it = 0; it < SPIN_MAX; it++) {
            bool ok = true;
#pragma unroll
            for (int k = 0; k < 3; k++)
                if (k < 2 || w < 10)
                    asm volatile("ld.relaxed.gpu.global.v4.u32 {%0,%1,%2,%3}, [%4];" : "=r"(hv[k][0]), "=r"(hv[k][1]), "=r"(hv[k][2]), "=r"(hv[k][3]) : "l"(hin + 128 * k) : "memory");
#pragma unroll
            for (int k = 0; k < 3; k++) ok = ok && hv[k][0] != ~0u && hv[k][1] != ~0u && hv[k][2] != ~0u && hv[k][3] != ~0u;
            if (ok) break;
        }
    }
    __syncwarp();
    TSTAMP1T(11, 256);
    const uint32_t hd = sbase + A1_SM_KV + (tid & 15) * A1_KVP + ((tid >> 4) & 1) * 16 + (w - 8) * 32;
#pragma unroll
    for (int k = 0; k < 3; k++)
        if (k < 2 || w < 10) stsm_x4(hd + 128 * k, hv[k][0], hv[k][1], hv[k][2], hv[k][3]);
    __syncwarp();
    if ((tid & 31) == 0) mbar_arrive(bar_kv);
}

constexpr int A2_THREADS = 288;
constexpr int A2_NA = 6;
#define A2_WPRE 4
#define A2_WLEAD 2
#define A2_RPOS 7
constexpr int A2_SM_A = 10 * WO_STAGE;
constexpr int A2_SM_R = A2_SM_A + A2_NA * 16384;
constexpr int A2_SM_BAR = A2_SM_R + 20480;
constexpr int A2_SMEM = A2_SM_BAR + 256 + 1024;

__global__ void __launch_bounds__(A2_THREADS, 1) a2_kernel(const int layer, const unsigned char* __restrict__ wo, const unsigned short* __restrict__ piv, float2* __restrict__ sum,
                                                           const __grid_constant__ CUtensorMap tmO, const __grid_constant__ CUtensorMap tmR,
                                                           const __grid_constant__ CUtensorMap tmX1) {
    extern __shared__ unsigned char smraw[];
    const uint32_t sbase = (smem_u32(smraw) + 1023) & ~1023u;
    const uint32_t bars = sbase + A2_SM_BAR, bar_e = bars + 80, bar_r = bars + 128;
    const int tid = threadIdx.x, w = __shfl_sync(~0u, tid >> 5, 0), wg = w >> 2;
    const int tile = sm_tile();
    if (tile >= 128) { sm_idle(2 * layer + 1); return; }
    const int mb = tile >> 3, cg = tile & 7;
    if (wg == 2) {
        const unsigned char* wsrc = wo + cg * 10 * WO_STAGE;
        if (tid == 256) {
            prefetch_tmap(&tmO);
#pragma unroll
            for (int i = 0; i < 17; i++) mbar_init(bars + 8 * i, i >= 10 && i < 16 ? 2 : 1);
            asm volatile("fence.mbarrier_init.release.cluster;" ::: "memory");
#pragma unroll
            for (int kb = 0; kb < A2_WPRE; kb += 2) {
                mbar_expect_tx(bars + 8 * kb, 16384 + 2 * WO_STAGE);
                bulk_load(sbase + kb * WO_STAGE, wsrc + kb * WO_STAGE, 2 * WO_STAGE, bars + 8 * kb);
            }
        }
        __syncwarp();
        asm volatile("bar.arrive 0, 288;" ::: "memory");
        if (tid == 256) {
#pragma unroll
            for (int kb = 0; kb < 10; kb++) if ((kb & 1) || kb >= A2_WPRE) mbar_expect_tx(bars + 8 * kb, (kb & 1) ? 16384 : 16384 + 2 * WO_STAGE);
            mbar_expect_tx(bar_r, 20480);
            pdl_sync();
#pragma unroll 1
            for (int kb = 0; kb < 10; kb++) {
                if (kb >= A2_NA) mbar_wait(bar_e + 8 * (kb - A2_NA), 0);
                tma_load_2d(sbase + A2_SM_A + (kb < A2_NA ? kb : kb - A2_NA) * 16384, &tmO, kb * 64, mb * 128, bars + 8 * kb);
                const int kw = kb + A2_WLEAD;
                if (!(kw & 1) && kw >= A2_WPRE && kw < 10) bulk_load(sbase + kw * WO_STAGE, wsrc + kw * WO_STAGE, 2 * WO_STAGE, bars + 8 * kw);
                if (kb == A2_RPOS) {
                    if (layer == 0) tma_load_2d(sbase + A2_SM_R, &tmR, cg * 80, mb * 128, bar_r);
                    else { tma_load_2d(sbase + A2_SM_R, &tmR, mb * 128, cg * 80, bar_r); tma_load_2d(sbase + A2_SM_R + 10240, &tmR, mb * 128 + 64, cg * 80, bar_r); }
                }
            }
        }
    } else {
        if (tid == 224) { prefetch_tmap(&tmR); prefetch_tmap(&tmX1); sm_started(2 * layer + 1); }
        asm volatile("bar.sync 0, 288;" ::: "memory");
        SPAN(2 + 4 * layer, 0);
        pdl_sync();
        SPAN(2 + 4 * layer, 1);
        TSTAMP2(0);
        TSTAMP4(0);
        if (threadIdx.x == 0) { GSTAMP(g_tim2, 15); }
        const int lane = tid & 31, warp = w, g = lane >> 2, t = lane & 3;
        const int row = layer * SEQ + mb * 128 + 16 * warp + g;
        const unsigned short pv0 = __ldcg(piv + row), pv1 = __ldcg(piv + row + 8);
        float acc[40];
        const uint64_t da0 = make_desc(sbase + A2_SM_A + wg * 8192, 16, 1024, 1), db0 = make_desc(sbase, 16, 1024, 1);
#pragma unroll 1
        for (int kb = 0; kb < 10; kb++) {
            if (kb == 0) TSTAMP4(11);
            mbar_wait(bars + 8 * kb, 0);
            TSTAMP4(1 + kb);
            wgmma_fence();
#pragma unroll
            for (int kk = 0; kk < 4; kk++) wgmma_n80<0, 0>(acc, da0 + (uint32_t)((kb < A2_NA ? kb : kb - A2_NA) * 1024 + kk * 2), db0 + (uint32_t)(kb * (WO_STAGE / 16) + kk * 2), kk ? 1 : kb);
            wgmma_commit();
            wgmma_wait<1>();
            if (kb > 0 && kb <= A2_NA && (tid & 127) == 0) mbar_arrive(bar_e + 8 * (kb - 1));
        }
        const uint32_t trow = ((lane & 7) + 8 * (lane >> 4)) * 128 + (((2 * (warp & 3) + ((lane >> 3) & 1)) ^ (lane & 7)) << 4);
        uint32_t xr[10][2];
        mbar_wait(bar_r, 0);
        if (layer == 0) {
#pragma unroll
            for (int j = 0; j < 10; j += 2) ldsm_x4(&xr[j][0], sbase + A2_SM_R + (16 * warp + (lane & 15)) * 160 + (lane >> 4) * 16 + 16 * j);
        } else {
#pragma unroll
            for (int j = 0; j < 10; j += 2) ldsm_x4_t(&xr[j][0], sbase + A2_SM_R + wg * 10240 + trow + 1024 * j);
        }
        mbar_wait(bar_e + 8 * (4 + wg), 0);
        wgmma_wait<0>();
        TSTAMP2(1);
        const float p0 = __uint_as_float((uint32_t)pv0 << 16), p1 = __uint_as_float((uint32_t)pv1 << 16);
        float s[4] = {0.f, 0.f, 0.f, 0.f};
#pragma unroll
        for (int j = 0; j < 10; j++) {
#pragma unroll
            for (int hh = 0; hh < 2; hh++) {
                const uint32_t a = pack2(acc[4 * j + 2 * hh], acc[4 * j + 2 * hh + 1]);
                const __nv_bfloat162 r = __hadd2_rn(*reinterpret_cast<const __nv_bfloat162*>(&xr[j][hh]), *reinterpret_cast<const __nv_bfloat162*>(&a));
                const uint32_t w = *reinterpret_cast<const uint32_t*>(&r);
                xr[j][hh] = w;
                const float d0 = __uint_as_float(w << 16) - (hh ? p1 : p0), d1 = __uint_as_float(w & 0xffff0000u) - (hh ? p1 : p0);
                s[2 * hh] += d0 + d1;
                s[2 * hh + 1] = fmaf(d0, d0, fmaf(d1, d1, s[2 * hh + 1]));
            }
        }
        const uint32_t so = sbase + A2_SM_A + (4 + wg) * 16384;
#pragma unroll
        for (int j = 0; j < 10; j += 2) stsm_x4_t(so + trow + 1024 * j, xr[j][0], xr[j][1], xr[j + 1][0], xr[j + 1][1]);
        fence_async_smem();
        TSTAMP2(2);
#pragma unroll
        for (int o = 1; o <= 2; o <<= 1)
#pragma unroll
            for (int i = 0; i < 4; i++) s[i] += __shfl_xor_sync(~0u, s[i], o);
        if (t < 2) asm volatile("red.relaxed.gpu.global.add.v2.f32 [%0], {%1, %2};" ::"l"(sum + layer * SEQ + (g >> 1) * 512 + (mb * 16 + 2 * warp + t) * 2 + (g & 1)), "f"(t ? s[2] : s[0]), "f"(t ? s[3] : s[1]) : "memory");
        if (wg) asm volatile("bar.sync 2, 128;" ::: "memory"); else asm volatile("bar.sync 1, 128;" ::: "memory");
        TSTAMP2(3);
        if ((tid & 127) == 0) tma_store_2d(&tmX1, mb * 128 + 64 * wg, cg * 80, so);
        TSTAMP2(4);
        GSTAMP(g_tim2, 14);
        SPAN(2 + 4 * layer, 3);
    }
}

static int h_nsm;
static void* h_sym[7];
static CUtensorMap h_tmX0, h_tmX1, h_tmOst, h_tmO, h_tmR0, h_tmR1, h_tmX1st, h_tmOut, h_tmWq, h_tmWo;
typedef CUresult (*PFN_encodeTiled)(CUtensorMap*, CUtensorMapDataType, cuuint32_t, void*, const cuuint64_t*, const cuuint64_t*,
                                    const cuuint32_t*, const cuuint32_t*, CUtensorMapInterleave, CUtensorMapSwizzle,
                                    CUtensorMapL2promotion, CUtensorMapFloatOOBfill);
static void make_tmap(CUtensorMap* tm, const void* ptr, uint64_t cols, uint64_t rows, uint32_t bc, uint32_t br, CUtensorMapSwizzle sw, uint64_t pitch = 0, uint64_t hi = 0) {
    static PFN_encodeTiled fn = nullptr;
    if (!fn) {
        void* p = nullptr; cudaDriverEntryPointQueryResult qr;
        cudaGetDriverEntryPoint("cuTensorMapEncodeTiled", &p, cudaEnableDefault, &qr);
        fn = (PFN_encodeTiled)p;
    }
    if (br == 0) {
        cuuint64_t dims[4] = {cols, 2, rows / 8, 4}; cuuint64_t strides[3] = {cols * 2, cols * 16, cols * 4};
        cuuint32_t box[4] = {bc, 2, 8, 4}; cuuint32_t es[4] = {1, 1, 1, 1};
        fn(tm, CU_TENSOR_MAP_DATA_TYPE_BFLOAT16, 4, const_cast<void*>(ptr), dims, strides, box, es, CU_TENSOR_MAP_INTERLEAVE_NONE, sw,
           CU_TENSOR_MAP_L2_PROMOTION_L2_128B, CU_TENSOR_MAP_FLOAT_OOB_FILL_NONE);
        return;
    }
    if (hi) {
        cuuint64_t dims[3] = {cols, rows, 32}; cuuint64_t strides[2] = {pitch * 2, hi * 2};
        cuuint32_t box[3] = {bc, br, 2}; cuuint32_t es[3] = {1, 1, 1};
        fn(tm, CU_TENSOR_MAP_DATA_TYPE_BFLOAT16, 3, const_cast<void*>(ptr), dims, strides, box, es, CU_TENSOR_MAP_INTERLEAVE_NONE, sw,
           CU_TENSOR_MAP_L2_PROMOTION_L2_128B, CU_TENSOR_MAP_FLOAT_OOB_FILL_NONE);
        return;
    }
    cuuint64_t dims[2] = {cols, rows}; cuuint64_t strides[1] = {(pitch ? pitch : cols) * 2};
    cuuint32_t box[2] = {bc, br}; cuuint32_t es[2] = {1, 1};
    fn(tm, CU_TENSOR_MAP_DATA_TYPE_BFLOAT16, 2, const_cast<void*>(ptr), dims, strides, box, es, CU_TENSOR_MAP_INTERLEAVE_NONE, sw,
       CU_TENSOR_MAP_L2_PROMOTION_L2_128B, CU_TENSOR_MAP_FLOAT_OOB_FILL_NONE);
}
template <typename... Args>
static void launch_pdl(void (*kern)(Args...), int grid, int block, int smem, Args... args) {
    cudaLaunchConfig_t cfg = {};
    cfg.gridDim = dim3(grid); cfg.blockDim = dim3(block); cfg.dynamicSmemBytes = smem; cfg.stream = cudaStreamPerThread;
    cudaLaunchAttribute at[1];
    at[0].id = cudaLaunchAttributeProgrammaticStreamSerialization; at[0].val.programmaticStreamSerializationAllowed = 1;
    cfg.attrs = at; cfg.numAttrs = 1;
    cudaLaunchKernelEx(&cfg, kern, args...);
}
static void launch_stage(int k, void* const* d_in, void* d_out) {
    const KgIn kg = {(const bf16*)d_in[4], (const bf16*)d_in[5], (const bf16*)d_in[6], (const bf16*)d_in[7], (const bf16*)d_in[8], (const bf16*)d_in[0], (const bf16*)d_in[1], (const bf16*)d_in[2],
                      (uint4*)h_sym[0], (uint4*)h_sym[1], (uint4*)h_sym[2], (uint4*)h_sym[3], (uint4*)h_sym[4], (float*)h_sym[5]};
    switch (k) {
        case 0: kgen_kernel<<<DM, KG_THREADS, 0, cudaStreamPerThread>>>(kg, h_tmWq, h_tmWo); break;
        case 1: launch_pdl(a1_kernel, h_nsm, A1_THREADS, A1_SMEM, 0, (const bf16*)d_in[0], (const unsigned char*)h_sym[1], h_tmX0, h_tmOst); break;
        case 2: launch_pdl(a2_kernel, h_nsm, A2_THREADS, A2_SMEM, 0, (const unsigned char*)h_sym[2], (const unsigned short*)h_sym[6], (float2*)h_sym[4], h_tmO, h_tmR0, h_tmX1st); break;
        case 3: launch_pdl(conv_kernel, DM / CV_CPB, CV_THREADS, CV_SMEM, (const bf16*)d_in[9], 0, h_tmOut); break;
        case 5: launch_pdl(a1_kernel, h_nsm, A1_THREADS, A1_SMEM, 1, (const bf16*)d_in[0], (const unsigned char*)h_sym[1], h_tmX1, h_tmOst); break;
        case 6: launch_pdl(a2_kernel, h_nsm, A2_THREADS, A2_SMEM, 1, (const unsigned char*)h_sym[2], (const unsigned short*)h_sym[6], (float2*)h_sym[4], h_tmO, h_tmR1, h_tmX1st); break;
        case 7: launch_pdl(conv_kernel, DM / CV_CPB, CV_THREADS, CV_SMEM, (const bf16*)d_in[9], 1, h_tmOut); break;
        default: break;
    }
}
static int n_stage_kernels() { return 9; }
static const char* stage_name(int k) { const char* n[] = {"kgen", "a1", "a2", "conv", "tr", "a1", "a2", "conv", "tr"}; return n[k]; }

extern "C" void kernel_launch(void* const* d_in, const int* in_sizes, int n_in, void* d_out, int out_size) {
    (void)in_sizes; (void)n_in; (void)out_size;
    static const void *p_in = nullptr, *p_w1 = nullptr, *p_w2 = nullptr, *p_out = nullptr;
    if (p_in != d_in[0] || p_w1 != d_in[1] || p_w2 != d_in[2] || p_out != d_out) {
        cudaFuncSetAttribute(conv_kernel, cudaFuncAttributeMaxDynamicSharedMemorySize, CV_SMEM);
        cudaFuncSetAttribute(kgen_kernel, cudaFuncAttributePreferredSharedMemoryCarveout, 100);
        cudaFuncSetAttribute(a1_kernel, cudaFuncAttributeMaxDynamicSharedMemorySize, A1_SMEM);
        cudaFuncSetAttribute(a2_kernel, cudaFuncAttributeMaxDynamicSharedMemorySize, A2_SMEM);
        int dev; cudaGetDevice(&dev); cudaDeviceGetAttribute(&h_nsm, cudaDevAttrMultiProcessorCount, dev);
        if (h_nsm != 132) h_nsm = 128;
        cudaGetSymbolAddress(&h_sym[0], g_tap); cudaGetSymbolAddress(&h_sym[1], g_wq); cudaGetSymbolAddress(&h_sym[2], g_wo);
        cudaGetSymbolAddress(&h_sym[3], g_halo); cudaGetSymbolAddress(&h_sym[4], g_sum); cudaGetSymbolAddress(&h_sym[5], g_csp); cudaGetSymbolAddress(&h_sym[6], g_piv);
        void *po, *px1, *px2;
        cudaGetSymbolAddress(&po, g_o); cudaGetSymbolAddress(&px1, g_x1T); cudaGetSymbolAddress(&px2, g_xcT);
        make_tmap(&h_tmO, po, 640, 2048, 64, 128, CU_TENSOR_MAP_SWIZZLE_128B);
        make_tmap(&h_tmOst, po, 640, 2048, 80, 16, CU_TENSOR_MAP_SWIZZLE_NONE);
        make_tmap(&h_tmX0, d_in[0], 640, 64, 64, 64, CU_TENSOR_MAP_SWIZZLE_128B, 640, 64 * 640);
        make_tmap(&h_tmX1, px2, 64, 640, 64, 64, CU_TENSOR_MAP_SWIZZLE_128B, XCP, 64);
        make_tmap(&h_tmR0, d_in[0], 640, 2048, 80, 128, CU_TENSOR_MAP_SWIZZLE_NONE);
        make_tmap(&h_tmR1, px2, 2048, 640, 64, 80, CU_TENSOR_MAP_SWIZZLE_128B, XCP);
        make_tmap(&h_tmX1st, px1, 2048, 640, 64, 80, CU_TENSOR_MAP_SWIZZLE_128B, XCP);
        make_tmap(&h_tmWq, d_in[1], 1920, 640, 32, 0, CU_TENSOR_MAP_SWIZZLE_64B);
        make_tmap(&h_tmWo, d_in[2], 640, 640, 32, 0, CU_TENSOR_MAP_SWIZZLE_64B);
        make_tmap(&h_tmOut, d_out, 640, 2048, 80, 8, CU_TENSOR_MAP_SWIZZLE_NONE);
        p_in = d_in[0]; p_w1 = d_in[1]; p_w2 = d_in[2]; p_out = d_out;
    }
    for (int k = 0; k < n_stage_kernels(); k++) launch_stage(k, d_in, d_out);
}
```

```cpp
#include <cuda_runtime.h>
#include <cuda_bf16.h>
#include <stdint.h>
#include <cuda.h>

typedef __nv_bfloat16 bf16;

constexpr int SEQ = 2048;
constexpr int DM = 640;
constexpr int NMODE = 192;

__device__ __forceinline__ float bf2f(bf16 v) { return __bfloat162float(v); }
__device__ __forceinline__ float rbf(float v) {
    uint32_t r;
    asm("cvt.rn.bf16x2.f32 %0, %1, %2;" : "=r"(r) : "f"(v), "f"(0.f));
    return __uint_as_float(r);
}
__device__ __forceinline__ uint32_t pack2(float lo, float hi) {
    __nv_bfloat162 t = __floats2bfloat162_rn(lo, hi);
    return *reinterpret_cast<uint32_t*>(&t);
}
__device__ __forceinline__ void pdl_sync() {
    asm volatile("griddepcontrol.wait;" ::: "memory");
    asm volatile("griddepcontrol.launch_dependents;" ::: "memory");
}
__device__ __forceinline__ float sqrt_apx(float v) { float r; asm("sqrt.approx.ftz.f32 %0, %1;" : "=f"(r) : "f"(v)); return r; }
__device__ __forceinline__ float rcp_apx(float v) { float r; asm("rcp.approx.ftz.f32 %0, %1;" : "=f"(r) : "f"(v)); return r; }
__device__ __forceinline__ uint32_t smem_u32(const void* p) { return (uint32_t)__cvta_generic_to_shared(p); }

constexpr int TPAD = 16;
constexpr int DLEN = 544;
constexpr int TAP_W2 = DLEN * 8, TAP_W3 = TAP_W2 + 768, TAP_C = TAP_W3 + 768, TAPB = TAP_C + 384;
__device__ __align__(128) uint4 g_tap[DM * 128];
#define XPAD 64
constexpr int XCP = SEQ + XPAD;
__device__ __align__(128) bf16 g_x1T[DM * XCP];
__device__ __align__(128) bf16 g_xcT[DM * XCP];
__device__ __align__(128) bf16 g_o[SEQ * DM];
constexpr int WQ_STAGE = 240 * 128, WO_STAGE = 80 * 128;
__device__ __align__(128) uint4 g_wq[8 * 10 * WQ_STAGE / 16];
__device__ __align__(128) uint4 g_wo[8 * 10 * WO_STAGE / 16];
__device__ __align__(16) float g_csp[10 * 1920];
__device__ __align__(16) float2 g_sum[2 * SEQ];
__device__ __align__(16) bf16 g_piv[2 * SEQ];
__device__ __align__(128) bf16 g_yT[DM * XCP];
__device__ uint32_t g_epoch;
__device__ __align__(16) unsigned long long g_rstat[SEQ];
__device__ ulonglong2 g_part[16 * 8 * 128];
__device__ uint4 g_halo[2 * 128 * 320];
__device__ __forceinline__ unsigned long long tagw(uint32_t payload, uint32_t tag) { return ((unsigned long long)tag << 32) | payload; }
__device__ __forceinline__ void st_tag2(ulonglong2* p, uint32_t a, uint32_t b, uint32_t tag) {
    asm volatile("st.global.cg.v2.u64 [%0], {%1, %2};" ::"l"(p), "l"(tagw(a, tag)), "l"(tagw(b, tag)) : "memory");
}
__device__ __forceinline__ ulonglong2 ld_tag2(const ulonglong2* p) {
    ulonglong2 v;
    asm volatile("ld.relaxed.gpu.global.v2.u64 {%0, %1}, [%2];" : "=l"(v.x), "=l"(v.y) : "l"(p) : "memory");
    return v;
}
__device__ __forceinline__ bool tag_ok(ulonglong2 v, uint32_t tag) { return (uint32_t)(v.x >> 32) == tag && (uint32_t)(v.y >> 32) == tag; }
__device__ __forceinline__ uint32_t ld_epoch() { uint32_t v; asm volatile("ld.relaxed.gpu.global.u32 %0, [%1];" : "=r"(v) : "l"(&g_epoch) : "memory"); return v + 1; }
constexpr int SPIN_MAX = 1 << 20;
__device__ uint32_t g_started[4];
__device__ __forceinline__ void sm_started(int slot) { asm volatile("red.relaxed.gpu.global.add.u32 [%0], 1;" ::"l"(g_started + slot) : "memory"); }
__device__ __noinline__ void sm_idle(int slot) {
    if (threadIdx.x) return;
    sm_started(slot);
    const uint32_t want = ld_epoch() * gridDim.x;
    pdl_sync();
#pragma unroll 1
    for (int it = 0; it < SPIN_MAX; it++) {
        uint32_t v;
        asm volatile("ld.relaxed.gpu.global.u32 %0, [%1];" : "=r"(v) : "l"(g_started + slot) : "memory");
        if ((int)(v - want) >= 0) break;
        __nanosleep(100);
    }
}
__device__ __forceinline__ int sm_tile() {
    uint32_t s, ns;
    asm volatile("mov.u32 %0, %smid;" : "=r"(s));
    asm volatile("mov.u32 %0, %nsmid;" : "=r"(ns));
    const uint32_t h = (s - 64) >> 1, q = (h * 37) >> 8;
    const int t0 = ((s >> 1) & 7) * 16 + (s >> 4) * 2 + (s & 1), t1 = (1 + h - 7 * q) * 16 + 8 + q * 2 + (s & 1), t2 = s - 124 < 8 ? s - 116 : 128;
    return gridDim.x != ns ? (int)blockIdx.x : s < 64 ? t0 : s < 120 ? t1 : t2;
}
#define DBG_SYMS
#define TSTAMP(i)
#define TSTAMP1(i)
#define TSTAMP1T(i, t)
#define TSTAMP1X(i, t)
#define SPAN(k, i)
#define GSTAMP(arr, i)
#define TSTAMP2(i)
#define TSTAMP3(i)
#define TSTAMP4(i)
#define TSTAMPK(i, t)

__device__ __forceinline__ void mma_bf16(float* d, uint32_t a0, uint32_t a1, uint32_t a2, uint32_t a3, uint32_t b0, uint32_t b1) {
    asm volatile("mma.sync.aligned.m16n8k16.row.col.f32.bf16.bf16.f32 {%0,%1,%2,%3}, {%4,%5,%6,%7}, {%8,%9}, {%0,%1,%2,%3};"
                 : "+f"(d[0]), "+f"(d[1]), "+f"(d[2]), "+f"(d[3]) : "r"(a0), "r"(a1), "r"(a2), "r"(a3), "r"(b0), "r"(b1));
}
__device__ __forceinline__ void mma_bf16_k8(float* d, uint32_t a0, uint32_t a1, uint32_t b0) {
    asm volatile("mma.sync.aligned.m16n8k8.row.col.f32.bf16.bf16.f32 {%0,%1,%2,%3}, {%4,%5}, {%6}, {%0,%1,%2,%3};"
                 : "+f"(d[0]), "+f"(d[1]), "+f"(d[2]), "+f"(d[3]) : "r"(a0), "r"(a1), "r"(b0));
}
__device__ __forceinline__ void ldsm_x4(uint32_t* r, uint32_t addr) {
    asm volatile("ldmatrix.sync.aligned.m8n8.x4.shared.b16 {%0,%1,%2,%3}, [%4];"
                 : "=r"(r[0]), "=r"(r[1]), "=r"(r[2]), "=r"(r[3]) : "r"(addr));
}

__device__ __forceinline__ void ldsm_x4_t(uint32_t* r, uint32_t addr) {
    asm volatile("ldmatrix.sync.aligned.m8n8.x4.trans.shared.b16 {%0,%1,%2,%3}, [%4];"
                 : "=r"(r[0]), "=r"(r[1]), "=r"(r[2]), "=r"(r[3]) : "r"(addr));
}
__device__ __forceinline__ void mbar_init(uint32_t bar, int count) { asm volatile("mbarrier.init.shared::cta.b64 [%0], %1;" ::"r"(bar), "r"(count)); }
__device__ __forceinline__ void mbar_arrive(uint32_t bar) { asm volatile("mbarrier.arrive.shared::cta.b64 _, [%0];" ::"r"(bar) : "memory"); }
__device__ __forceinline__ void mbar_wait(uint32_t bar, uint32_t parity) {
    asm volatile("{\n.reg .pred p;\nWAIT_LOOP:\n"
                 "mbarrier.try_wait.parity.shared::cta.b64 p, [%0], %1;\n"
                 "@p bra.uni WAIT_DONE;\nbra.uni WAIT_LOOP;\nWAIT_DONE:\n}" ::"r"(bar), "r"(parity) : "memory");
}

__device__ __forceinline__ void mbar_expect_tx(uint32_t bar, uint32_t bytes) {
    asm volatile("mbarrier.arrive.expect_tx.shared::cta.b64 _, [%0], %1;" ::"r"(bar), "r"(bytes) : "memory");
}
__device__ __forceinline__ void tma_load_2d(uint32_t dst, const void* tmap, int c0, int c1, uint32_t bar) {
    asm volatile("cp.async.bulk.tensor.2d.shared::cluster.global.mbarrier::complete_tx::bytes [%0], [%1, {%3, %4}], [%2];"
                 ::"r"(dst), "l"(tmap), "r"(bar), "r"(c0), "r"(c1) : "memory");
}
__device__ __forceinline__ void tma_load_3d(uint32_t dst, const void* tmap, int c0, int c1, int c2, uint32_t bar) {
    asm volatile("cp.async.bulk.tensor.3d.shared::cluster.global.mbarrier::complete_tx::bytes [%0], [%1, {%3, %4, %5}], [%2];"
                 ::"r"(dst), "l"(tmap), "r"(bar), "r"(c0), "r"(c1), "r"(c2) : "memory");
}
__device__ __forceinline__ void fence_async_smem() { asm volatile("fence.proxy.async.shared::cta;" ::: "memory"); }
__device__ __forceinline__ void bulk_load(uint32_t dst, const void* src, uint32_t bytes, uint32_t bar) {
    asm volatile("cp.async.bulk.shared::cluster.global.mbarrier::complete_tx::bytes [%0], [%1], %2, [%3];"
                 ::"r"(dst), "l"(src), "r"(bytes), "r"(bar) : "memory");
}
__device__ __forceinline__ void tma_store_2d(const void* tmap, int c0, int c1, uint32_t src) {
    asm volatile("cp.async.bulk.tensor.2d.global.shared::cta.bulk_group [%0, {%1, %2}], [%3];" ::"l"(tmap), "r"(c0), "r"(c1), "r"(src) : "memory");
    asm volatile("cp.async.bulk.commit_group;" ::: "memory");
    asm volatile("cp.async.bulk.wait_group.read 0;" ::: "memory");
}
__device__ __forceinline__ void stsm_x4(uint32_t addr, uint32_t r0, uint32_t r1, uint32_t r2, uint32_t r3) {
    asm volatile("stmatrix.sync.aligned.m8n8.x4.shared.b16 [%0], {%1,%2,%3,%4};" ::"r"(addr), "r"(r0), "r"(r1), "r"(r2), "r"(r3) : "memory");
}
__device__ __forceinline__ void stsm_x4_t(uint32_t addr, uint32_t r0, uint32_t r1, uint32_t r2, uint32_t r3) {
    asm volatile("stmatrix.sync.aligned.m8n8.x4.trans.shared.b16 [%0], {%1,%2,%3,%4};" ::"r"(addr), "r"(r0), "r"(r1), "r"(r2), "r"(r3) : "memory");
}
__device__ __forceinline__ void prefetch_tmap(const void* tmap) { asm volatile("prefetch.tensormap [%0];" ::"l"(tmap) : "memory"); }

__device__ __forceinline__ float2 cexp_at(float wr2, float wi, float p) {
    float er;
    asm("ex2.approx.ftz.f32 %0, %1;" : "=f"(er) : "f"(wr2 * p));
    float th = wi * p;
    const float k = rintf(th * 0.15915494309189535f);
    th = fmaf(k, -6.2831854820251465f, th);
    th = fmaf(k, 1.7484555314695172e-7f, th);
    return make_float2(er * __cosf(th), er * __sinf(th));
}
__device__ __forceinline__ float2 cmul(float2 a, float2 b) {
    return make_float2(fmaf(a.x, b.x, -a.y * b.y), fmaf(a.x, b.y, a.y * b.x));
}
__device__ __forceinline__ float2 csqr(float2 a) { return make_float2(fmaf(a.x, a.x, -a.y * a.y), (a.x + a.x) * a.y); }
__device__ __forceinline__ uint32_t packh(float2 v) {
    uint32_t r;
    asm("cvt.rn.f16x2.f32 %0, %1, %2;" : "=r"(r) : "f"(v.y), "f"(v.x));
    return r;
}
__device__ __forceinline__ void mma_f16(float* d, uint32_t a0, uint32_t a1, uint32_t a2, uint32_t a3, uint32_t b0, uint32_t b1) {
    asm volatile("mma.sync.aligned.m16n8k16.row.col.f32.f16.f16.f32 {%0,%1,%2,%3}, {%4,%5,%6,%7}, {%8,%9}, {%0,%1,%2,%3};"
                 : "+f"(d[0]), "+f"(d[1]), "+f"(d[2]), "+f"(d[3]) : "r"(a0), "r"(a1), "r"(a2), "r"(a3), "r"(b0), "r"(b1));
}

struct KgIn { const bf16 *logA, *Aim, *Cre, *Cim, *logdt, *x, *wqkv, *wo; uint4 *tap, *wq, *wop, *halo, *sum; float* csp; };
constexpr int KG_THREADS = NMODE / 2;

__global__ void __launch_bounds__(KG_THREADS, 5) kgen_kernel(const KgIn in, const __grid_constant__ CUtensorMap tmWq, const __grid_constant__ CUtensorMap tmWo) {
    __shared__ __align__(8) unsigned long long wbar[3];
    __shared__ __align__(1024) uint4 tab[3 * 896];
    const int d = blockIdx.x, tid = threadIdx.x, lane = tid & 31, warp = __shfl_sync(~0u, tid >> 5, 0);
    SPAN(0, 0); SPAN(0, 1);
    TSTAMPK(0, 0);
    asm volatile("griddepcontrol.launch_dependents;" ::: "memory");
    const bf16 pdt = in.logdt[d];
    const uint32_t pla = reinterpret_cast<const uint32_t*>(in.logA)[d * KG_THREADS + tid], pai = reinterpret_cast<const uint32_t*>(in.Aim)[d * KG_THREADS + tid];
    const uint32_t pcr = reinterpret_cast<const uint32_t*>(in.Cre)[d * KG_THREADS + tid], pci = reinterpret_cast<const uint32_t*>(in.Cim)[d * KG_THREADS + tid];
    const bf16* pfq = tid < 30 ? in.wqkv + (size_t)(d * 30 + tid) * 64 : tid < 40 ? in.wo + (size_t)(d * 10 + tid - 30) * 64 : in.x + (size_t)(d * 32 + tid - 40) * 64;
    if (tid < 72) asm volatile("prefetch.global.L2 [%0];" ::"l"(pfq));
    asm volatile("st.global.v4.u32 [%0], {%1,%1,%1,%1};" ::"l"(in.halo + d * 128 + tid), "r"(~0u));
    if (tid < 32) asm volatile("st.global.v4.u32 [%0], {%1,%1,%1,%1};" ::"l"(in.halo + d * 128 + 96 + tid), "r"(~0u));
    const uint32_t tw = smem_u32(tab) + warp * 14336;
    if (lane == 0) { mbar_init(smem_u32(wbar + warp), 1); prefetch_tmap(d >= 200 ? &tmWo : &tmWq); }
    const int g = lane >> 2, t = lane & 3;
    const uint32_t sta = tw + lane * 128 + ((2 * (lane & 3) + ((lane >> 2) & 1)) << 4);
    const uint32_t lda = tw + t * 128 + ((g ^ (2 * t)) << 4);
    const uint32_t stb = tw + 12288 + lane * 64 + ((4 * ((lane >> 1) & 1) + ((lane >> 2) & 3)) << 3);
    const uint32_t ldb = tw + 12288 + t * 64 + ((g ^ (4 * (t >> 1))) << 3);
    auto sts4 = [&](int e, int off, uint32_t a, uint32_t b, uint32_t c, uint32_t dd) {
        asm volatile("st.shared.v4.u32 [%0], {%1,%2,%3,%4};" ::"r"((sta ^ (e << 4)) + off), "r"(a), "r"(b), "r"(c), "r"(dd) : "memory");
    };
    auto lds4 = [&](int sp, int off, uint32_t* r) {
        asm volatile("ld.shared.v4.u32 {%0,%1,%2,%3}, [%4];" : "=r"(r[0]), "=r"(r[1]), "=r"(r[2]), "=r"(r[3]) : "r"((lda ^ ((sp & 1) << 4)) + sp * 512 + off) : "memory");
    };
    const float dt = rbf(expf(bf2f(pdt)));
    float2 C[2], y1[2], z8[2], y128[2];
    float cmax = 0.f;
#pragma unroll
    for (int m = 0; m < 2; m++) {
        const float wr2 = -rbf(expf(__uint_as_float(m ? pla & 0xffff0000u : pla << 16))) * dt * 1.4426950408889634f;
        const float wi = __uint_as_float(m ? pai & 0xffff0000u : pai << 16) * dt;
        C[m] = make_float2(__uint_as_float(m ? pcr & 0xffff0000u : pcr << 16) * dt, -__uint_as_float(m ? pci & 0xffff0000u : pci << 16) * dt);
        cmax = fmaxf(cmax, fmaxf(fabsf(C[m].x), fabsf(C[m].y)));
        y1[m] = cexp_at(wr2, -wi, 1.f); z8[m] = cexp_at(wr2, wi, 8.f); y128[m] = cexp_at(wr2, -wi, 128.f);
    }
    const int ex = min(max((int)(__reduce_max_sync(~0u, __float_as_uint(cmax)) >> 23), 20), 240);
    const float scale = __uint_as_float((uint32_t)(127 + 10 + 127 - ex) << 23), unscale = 2.0f * __uint_as_float((uint32_t)(ex - 10) << 23);
    TSTAMPK(4, 0);
    float k2048 = 0.f;
    float acc[5][4];
#pragma unroll
    for (int j = 0; j < 5; j++)
#pragma unroll
        for (int k = 0; k < 4; k++) acc[j][k] = 0.f;
    uint32_t af[8][4];
    {
        float2 h0[2], h1[2], g0[2], g1[2], g2[2], g2b[2], g3[2], g4[2], y2[2], y4[2];
#pragma unroll
        for (int m = 0; m < 2; m++) {
            h0[m] = make_float2(1.f, 0.f); h1[m] = csqr(csqr(csqr(z8[m])));
            g0[m] = make_float2(C[m].x * scale, C[m].y * scale);
            g1[m] = cmul(g0[m], y128[m]);
            const float2 y256 = csqr(y128[m]), y512 = csqr(y256);
            g2b[m] = g2[m] = cmul(g0[m], y256); g3[m] = cmul(g0[m], y512); g4[m] = cmul(g3[m], y512);
            y2[m] = csqr(y1[m]); y4[m] = csqr(y2[m]);
            const float2 y1024 = csqr(y512);
            k2048 += fmaf(g4[m].x, y1024.x, -g4[m].y * y1024.y);
        }
#pragma unroll
        for (int e = 0; e < 8; e++) {
            sts4(e, 0, packh(h0[0]), packh(h1[0]), packh(h0[1]), packh(h1[1]));
            sts4(e, 4096, packh(g0[0]), packh(g0[1]), packh(g1[0]), packh(g1[1]));
#pragma unroll
            for (int m = 0; m < 2; m++)
                if (e < 7) { h0[m] = e ? cmul(h0[m], z8[m]) : z8[m]; h1[m] = cmul(h1[m], z8[m]); g0[m] = cmul(g0[m], y1[m]); g1[m] = cmul(g1[m], y1[m]); }
            if (e < 5) k2048 += __shfl_xor_sync(~0u, k2048, 1 << e);
        }
        __syncwarp();
#pragma unroll
        for (int e = 0; e < 8; e++) {
            uint32_t b[4];
            lds4(e, 0, af[e]); lds4(e, 4096, b);
            sts4(e, 8192, packh(g2[0]), packh(g2[1]), packh((e & 1) ? cmul(g3[0], y4[0]) : g3[0]), packh((e & 1) ? cmul(g3[1], y4[1]) : g3[1]));
            asm volatile("st.shared.v2.u32 [%0], {%1,%2};" ::"r"(stb ^ (e << 3)), "r"(packh(g4[0])), "r"(packh(g4[1])) : "memory");
#pragma unroll
            for (int m = 0; m < 2; m++)
                if (e < 7) {
                    g2[m] = e == 3 ? cmul(g2b[m], y128[m]) : cmul(g2[m], y2[m]);
                    if (e & 1) g3[m] = cmul(g3[m], y128[m]);
                    g4[m] = cmul(g4[m], y128[m]);
                }
            mma_f16(acc[0], af[e][0], af[e][1], af[e][2], af[e][3], b[0], b[1]);
            mma_f16(acc[1], af[e][0], af[e][1], af[e][2], af[e][3], b[2], b[3]);
        }
    }
    TSTAMPK(6, 0);
    const int job = d * 3 + warp;
    const bool isq = job < 600;
    const int j2 = isq ? job : job - 600, scol = (j2 / 10) * 32, skb = j2 - (j2 / 10) * 10;
    fence_async_smem();
    __syncwarp();
    if (job < 800) {
        if (lane == 0) {
            mbar_expect_tx(smem_u32(wbar + warp), 4096);
            asm volatile("cp.async.bulk.tensor.4d.shared::cluster.global.mbarrier::complete_tx::bytes [%0], [%1, {%3, %4, %5, %4}], [%2];"
                         ::"r"(tw + 4096), "l"(isq ? &tmWq : &tmWo), "r"(smem_u32(wbar + warp)), "r"(scol), "r"(0), "r"(skb * 8) : "memory");
        }
    } else if (job < 800 + 64) in.sum[(job - 800) * 32 + lane] = make_uint4(0, 0, 0, 0);
#pragma unroll
    for (int sp = 0; sp < 8; sp++) {
        uint32_t c[4], e0, e1;
        lds4(sp, 8192, c);
        asm volatile("ld.shared.v2.u32 {%0,%1}, [%2];" : "=r"(e0), "=r"(e1) : "r"((ldb ^ ((sp & 3) << 3)) + sp * 256) : "memory");
        mma_f16(acc[2], af[sp][0], af[sp][1], af[sp][2], af[sp][3], c[0], c[1]);
        mma_f16(acc[3], af[sp][0], af[sp][1], af[sp][2], af[sp][3], c[2], c[3]);
        mma_f16(acc[4], af[sp][0], af[sp][1], af[sp][2], af[sp][3], e0, e1);
    }
    {
        float* Pp = reinterpret_cast<float*>(tab + warp * 896);
#pragma unroll
        for (int h = 0; h < 2; h++) {
            const int b = g + 8 * h;
            *reinterpret_cast<float2*>(Pp + 8 * b + 2 * t) = make_float2(acc[0][2 * h] * unscale, acc[0][2 * h + 1] * unscale);
            *reinterpret_cast<float2*>(Pp + 128 + 8 * b + 2 * t) = make_float2(acc[1][2 * h] * unscale, acc[1][2 * h + 1] * unscale);
            *reinterpret_cast<float2*>(Pp + 256 + 4 * b + 2 * (t & 1) + 64 * (t >> 1)) = make_float2(acc[2][2 * h] * unscale, acc[2][2 * h + 1] * unscale);
            *reinterpret_cast<float2*>(Pp + 384 + 2 * b + 32 * t) = make_float2(acc[3][2 * h] * unscale, acc[3][2 * h + 1] * unscale);
            Pp[512 + b + 32 * t] = acc[4][2 * h] * unscale;
            Pp[512 + b + 32 * t + 16] = acc[4][2 * h + 1] * unscale;
        }
        if (lane == 0) Pp[640] = k2048 * unscale;
    }
    TSTAMPK(7, 0);
    __syncthreads();
    TSTAMPK(9, 0);
    const float* Kp = reinterpret_cast<const float*>(tab);
    auto ksum = [&](int i) -> float { return (Kp[i] + Kp[3584 + i]) + Kp[7168 + i]; };
    auto ksum4 = [&](int q) -> float4 {
        const float4 a = reinterpret_cast<const float4*>(Kp)[q], b = reinterpret_cast<const float4*>(Kp)[896 + q], c = reinterpret_cast<const float4*>(Kp)[1792 + q];
        return make_float4((a.x + b.x) + c.x, (a.y + b.y) + c.y, (a.z + b.z) + c.z, (a.w + b.w) + c.w);
    };
    {
        uint2* E4 = reinterpret_cast<uint2*>(in.tap + d * 128);
        float4 v = ksum4(tid), u = ksum4(96 + min(tid, 64));
        const float cor = rbf(ksum(tid == 95 ? 384 : 512));
        if (tid == 95) v.w -= cor;
        if (tid == 31) u.w -= cor;
        const uint32_t lo = pack2(v.x, v.y), hi = pack2(v.z, v.w);
        if (tid < 64) {
            E4[6 + tid] = make_uint2(lo, hi);
            E4[(tid < 32 ? 159 : 209 - 32) + tid] = make_uint2(pack2(u.x, u.y), pack2(u.z, u.w));
        } else {
            const uint32_t nx = __shfl_down_sync(~0u, lo, 1);
            in.tap[d * 128 + 35 + tid - 64] = make_uint4(__byte_perm(lo, 0, 0x1010), __byte_perm(lo, hi, 0x5432), __byte_perm(hi, 0, 0x1010), __byte_perm(hi, tid == 95 ? 0u : nx, 0x5432));
            if (tid == 64) E4[241] = make_uint2(pack2(u.x, 0.f), 0u);
        }
    }
    TSTAMPK(10, 0);
    if (job < 800) {
        mbar_wait(smem_u32(wbar + warp), 0);
        const uint32_t src = tw + 4096 + ((lane >> 3) * 16 + (lane & 7)) * 64;
#pragma unroll
        for (int cg = 0; cg < 4; cg++) {
            const int col = scol + 8 * cg, sec = col / DM, r = col - sec * DM, hg = r / 80;
            const int n = isq ? hg * 160 + sec * 80 + r : col;
            unsigned char* dst = (isq ? reinterpret_cast<unsigned char*>(in.wq) + (hg * 9 + skb) * WQ_STAGE : reinterpret_cast<unsigned char*>(in.wop) + (hg * 9 + skb) * WO_STAGE) + (n + g) * 128;
            float cs[4] = {0.f, 0.f, 0.f, 0.f};
#pragma unroll
            for (int h = 0; h < 2; h++) {
                uint32_t w[4];
                ldsm_x4_t(w, src + h * 512 + ((cg ^ ((lane >> 1) & 3)) << 4));
                *reinterpret_cast<uint4*>(dst + (((4 * h + t) ^ g) << 4)) = make_uint4(w[0], w[1], w[2], w[3]);
                if (isq) {
                    mma_bf16(cs, 0x3f803f80u, 0u, 0x3f803f80u, 0u, w[0], w[1]);
                    mma_bf16(cs, 0x3f803f80u, 0u, 0x3f803f80u, 0u, w[2], w[3]);
                }
            }
            if (isq && g == cg) *reinterpret_cast<float2*>(in.csp + skb * 1920 + n + 2 * t) = make_float2(cs[0], cs[1]);
        }
    }
    TSTAMPK(11, 0);
    SPAN(0, 3);
}

#define CV_MODE 0
#define CV_SLEEP 100
constexpr int CV_CPB = 5;
constexpr int CV_THREADS = 512;
constexpr int UPADF = 128;
constexpr int ULEN = UPADF + SEQ + 80;
constexpr int XLEN = SEQ + 16;
constexpr int BX_5 = 0, BX_3 = 3264, BX_9 = 6528, BX_7 = 8960, BX_LEN = 11392;
constexpr int CV_SM_T = 0;
constexpr int CV_SM_B = CV_CPB * TAPB;
constexpr int CV_SM_U = CV_SM_B + CV_CPB * BX_LEN;
constexpr int CV_SM_X = CV_SM_U + CV_CPB * ULEN * 2;
constexpr int CV_SM_Y = CV_SM_X + CV_CPB * XLEN * 2;
constexpr int CV_SM_P = CV_SM_Y + CV_CPB * XLEN * 2;
constexpr int CV_SM_CNT = CV_SM_P + 6 * 4096;
constexpr int CV_SM_O = (CV_SM_CNT + 128 + 127) & ~127;
constexpr int CV_SMEM = CV_SM_O + 20480;
static_assert(CV_SM_B % 128 == 0 && CV_SM_CNT % 16 == 0, "layout");

__device__ __forceinline__ uint32_t ln2(uint32_t x, uint32_t m, float ra, float rb) {
    const __nv_bfloat162 d = __hsub2(*reinterpret_cast<const __nv_bfloat162*>(&x), *reinterpret_cast<const __nv_bfloat162*>(&m));
    const uint32_t w = *reinterpret_cast<const uint32_t*>(&d);
    return pack2(__uint_as_float(w << 16) * ra, __uint_as_float(w & 0xffff0000u) * rb);
}
__device__ __forceinline__ void cp_async16(uint32_t dst, const void* src) {
    asm volatile("cp.async.cg.shared.global [%0], [%1], 16;" ::"r"(dst), "l"(src));
}
__device__ __forceinline__ void cp_async_wait_all() { asm volatile("cp.async.wait_all;" ::: "memory"); }

template <bool FULL>
__device__ __forceinline__ void direct_pass(float (&acc)[8][4], uint32_t ub, uint32_t o0, uint32_t o1, const uint2* __restrict__ Tp, bool first_half) {
    uint32_t sw[8][8];
#pragma unroll
    for (int j = 0; j < 8; j++) { ldsm_x4(&sw[j][0], ub + o0 + j * 256); ldsm_x4(&sw[j][4], ub + o1 + j * 256); }
#pragma unroll
    for (int M = 0; M < 4; M++) {
#pragma unroll
        for (int i = 0; i < 4; i++) {
            const uint2 hi = Tp[128 * M + 16 * i], lo = Tp[128 * M + 16 * i - 8];
#pragma unroll
            for (int j = FULL ? 0 : M; j < 8; j++) mma_bf16(acc[j], hi.x, hi.y, lo.x, lo.y, sw[(j - M) & 7][2 * i], sw[(j - M) & 7][2 * i + 1]);
        }
        if (FULL) {
            ldsm_x4(&sw[7 - M][0], ub + o0 - (M + 1) * 256);
            if (M < 3) ldsm_x4(&sw[7 - M][4], ub + o1 - (M + 1) * 256);
        }
    }
    if (first_half) {
        const uint2 hi = Tp[512], lo = Tp[504];
#pragma unroll
        for (int j = FULL ? 0 : 4; j < 8; j++) mma_bf16(acc[j], hi.x, hi.y, lo.x, lo.y, sw[(j - 4) & 7][0], sw[(j - 4) & 7][1]);
    }
}
__device__ __forceinline__ uint32_t fin2(uint32_t x, uint32_t y, uint32_t u, uint32_t dk) {
    typedef __nv_bfloat162 b2;
    const b2 r = __hadd2_rn(*reinterpret_cast<const b2*>(&x), __hadd2_rn(*reinterpret_cast<const b2*>(&y),
                            __hmul2_rn(*reinterpret_cast<const b2*>(&u), *reinterpret_cast<const b2*>(&dk))));
    return *reinterpret_cast<const uint32_t*>(&r);
}
__global__ void __launch_bounds__(CV_THREADS, 1) conv_kernel(const bf16* __restrict__ Dskip, int layer, const __grid_constant__ CUtensorMap tmOut) {
    extern __shared__ __align__(128) unsigned char sm[];
    SPAN(3 + 4 * layer, 0);
    bf16* Us = reinterpret_cast<bf16*>(sm + CV_SM_U);
    bf16* Xs = reinterpret_cast<bf16*>(sm + CV_SM_X);
    bf16* Ys = reinterpret_cast<bf16*>(sm + CV_SM_Y);
    const int tid = threadIdx.x, lane = tid & 31, warp = __shfl_sync(~0u, tid >> 5, 0);
    const int d0 = blockIdx.x * CV_CPB, tile = blockIdx.x; (void)tile;
    const int g = lane >> 2, ti = lane & 3;
    const int e = g - 2 * ti;
    uint32_t lds_off[4];
    uint32_t off2, off3, offc;
    {
        const int mat = lane >> 3, r = lane & 7;
#pragma unroll
        for (int pr = 0; pr < 4; pr++) {
            const int iw = 2 * pr + (mat >> 1), half = mat & 1;
            const int chunk = (UPADF - 16 * iw + 16 * r + 8 * half) >> 3;
            lds_off[pr] = (uint32_t)((chunk ^ ((chunk >> 3) & 1)) * 16);
        }
        const int j2 = 13 + r + 8 * (mat >> 1), j3 = j2 + 2, i0 = 8 * (mat & 1);
        off2 = (j2 & 1) ? BX_3 + (4 * j2 + i0 + 84) * 2 : BX_5 + (4 * j2 + i0 + 80) * 2;
        off3 = ((j3 & 1) ? BX_7 : BX_9) + (8 * j3 + i0 + 136) * 2;
        const int cc = (UPADF + 16 * (r + (mat >> 1)) + i0) >> 3;
        offc = (uint32_t)((cc ^ ((cc >> 3) & 1)) * 16);
    }
#define CV_WX 0
    const int wv = warp ^ CV_WX;
    const uint32_t rtab = wv < 8 ? (wv < 4 ? 0x0B090200u : 0x0C0A0301u) : (wv < 12 ? 0x13111008u : 0x1412241Cu);
    const int rl = (rtab >> (8 * (warp & 3))) & 0xff, type = rl >> 3, c = rl & 7;
    const int H = (type == 1 || type == 2) ? 1 : 0, T0 = 8 * H;
    uint32_t toff = CV_SM_T + c * TAPB + (TPAD + e) * 8;
    uint32_t ubase = smem_u32(Us + c * ULEN);
    const uint32_t bbase = smem_u32(sm + CV_SM_B + c * BX_LEN);
    uint32_t rd0, rd1;
    {
        const uint32_t rstart = wv < 8 ? (wv < 4 ? 0x02000000u : 0x06040000u) : (wv < 12 ? 0x0C0B0A08u : 0x1E1D150Fu);
        const uint32_t rcount = wv < 8 ? 0x02020000u : (wv < 12 ? 0x03010102u : 0x01010806u);
        rd0 = (rstart >> (8 * (warp & 3))) & 0xff; rd1 = rd0 + ((rcount >> (8 * (warp & 3))) & 0xff);
    }
    asm volatile("" : "+r"(lds_off[0]), "+r"(lds_off[1]), "+r"(lds_off[2]), "+r"(lds_off[3]), "+r"(ubase), "+r"(toff), "+r"(rd0), "+r"(rd1));
    const uint2* Tc = reinterpret_cast<const uint2*>(sm + toff);
    TSTAMP1X(9, 256);
    unsigned short dskr;
    asm volatile("ld.global.nc.u16 %0, [%1];" : "=h"(dskr) : "l"(Dskip + d0 + min(lane, CV_CPB - 1)));
    if (tid >= 256) {
        const int t2 = tid - 256;
        if (t2 == 0) {
            mbar_init(smem_u32(sm + CV_SM_CNT) + 104, 1);
            asm volatile("fence.mbarrier_init.release.cluster;" ::: "memory");
            mbar_expect_tx(smem_u32(sm + CV_SM_CNT) + 104, CV_CPB * 2048);
            bulk_load(smem_u32(sm + CV_SM_O), g_tap + d0 * 128, CV_CPB * 2048, smem_u32(sm + CV_SM_CNT) + 104);
        } else if (lane == 0) {
            mbar_init(smem_u32(sm + CV_SM_CNT) + 16 * (warp - 9), warp == 15 ? 16 : 1);
            if (warp < 15) mbar_init(smem_u32(sm + CV_SM_CNT) + 16 * (warp - 9) + 8, 1);
            else if (layer) prefetch_tmap(&tmOut);
        }
        if (t2 < 149) {
            const int k = t2;
            const int off = k < 18 ? BX_5 + 8 * k : k < 37 ? BX_3 + 8 * (k - 18) : k < 69 ? BX_9 + 8 * (k - 37) : k < 101 ? BX_7 + 8 * (k - 69)
                          : k < 133 ? 8 * (k - 101) : (UPADF + SEQ) * 2 + 8 * (k - 133);
#pragma unroll
            for (int c = 0; c < CV_CPB; c++) *reinterpret_cast<uint2*>(sm + (k < 101 ? CV_SM_B + c * BX_LEN : CV_SM_U + c * ULEN * 2) + off) = make_uint2(0, 0);
        }
        asm volatile("bar.sync 1, 256;" ::: "memory");
        TSTAMP1X(10, 256);
        mbar_wait(smem_u32(sm + CV_SM_CNT) + 104, 0);
        TSTAMP1X(11, 256);
#pragma unroll 1
        for (int r = t2; r < 392; r += 256) {
            const bool dd = r < 272, cc = r >= 368;
            const uint32_t* E2 = reinterpret_cast<const uint32_t*>(sm + CV_SM_O) + (dd ? r + 3 : r < 320 ? 301 + 2 * (r - 272) : cc ? 417 : 401 + 2 * (r - 320));
            const uint32_t* E3 = E2 + (dd ? 4 : cc ? 0 : 1);
            const uint32_t s0 = !cc ? 0x7610u : r == 382 ? 0x1044u : 0x4444u, s1 = !cc ? 0x7610u : r == 378 ? 0x1044u : 0x4444u;
            const uint32_t s2 = !cc ? 0x1032u : r == 381 ? 0x4410u : 0x4444u, s3 = !cc ? 0x1032u : r == 377 ? 0x4410u : 0x4444u;
            uint32_t w[CV_CPB][4];
#pragma unroll
            for (int c = 0; c < CV_CPB; c++) { w[c][0] = E2[512 * c]; w[c][1] = E2[512 * c + 1]; w[c][2] = E3[512 * c]; w[c][3] = E3[512 * c + 1]; }
#pragma unroll
            for (int c = 0; c < CV_CPB; c++) {
                const uint32_t a = __byte_perm(w[c][3], w[c][2], s1), b = __byte_perm(w[c][1], w[c][0], s2);
                *reinterpret_cast<uint4*>(sm + CV_SM_T + c * TAPB + r * 16) =
                    make_uint4(__byte_perm(w[c][1], w[c][0], s0), dd || cc ? a : b, dd || cc ? b : a, __byte_perm(w[c][3], w[c][2], s3));
            }
        }
        TSTAMP1X(12, 256);
        if (layer == 0) {
#pragma unroll
            for (int c = 0; c < CV_CPB; c++) reinterpret_cast<uint4*>(g_yT + (size_t)(d0 + c) * XCP)[t2] = make_uint4(~0u, ~0u, ~0u, ~0u);
        }
        pdl_sync();
        if (layer && blockIdx.x == 0 && t2 == 0) g_epoch = ld_epoch();
    } else {
        const uint4* ppv = reinterpret_cast<const uint4*>(g_piv + layer * SEQ) + tid;
        const float4* psv = reinterpret_cast<const float4*>(g_sum + layer * SEQ) + tid;
        const uint4* pxv = reinterpret_cast<const uint4*>(g_x1T + (size_t)d0 * XCP) + tid;
        asm volatile("" : "+l"(ppv), "+l"(psv), "+l"(pxv));
        pdl_sync();
        SPAN(3 + 4 * layer, 1);
        TSTAMP(0);
        if (threadIdx.x == 0) { GSTAMP(g_tim, 15); }
        float4 sv[4];
#pragma unroll
        for (int k = 0; k < 4; k++) sv[k] = __ldcg(psv + 256 * k);
        const uint4 pv = __ldcg(ppv);
        uint4 xv[CV_CPB];
#pragma unroll
        for (int c = 0; c < CV_CPB; c++) xv[c] = __ldcg(pxv + c * (XCP / 8));
        uint32_t mw[4];
        float rs[8];
#pragma unroll
        for (int k = 0; k < 4; k++) {
            const uint32_t pw = k == 0 ? pv.x : k == 1 ? pv.y : k == 2 ? pv.z : pv.w;
            const float d0_ = sv[k].x * (1.0f / DM), d1_ = sv[k].z * (1.0f / DM);
            mw[k] = pack2(__uint_as_float(pw << 16) + d0_, __uint_as_float(pw & 0xffff0000u) + d1_);
            const uint32_t vr = pack2(fmaxf(fmaf(-d0_, d0_, sv[k].y * (1.0f / DM)), 0.f), fmaxf(fmaf(-d1_, d1_, sv[k].w * (1.0f / DM)), 0.f));
            const uint32_t ve = pack2(__uint_as_float(vr << 16) + 1e-5f, __uint_as_float(vr & 0xffff0000u) + 1e-5f);
            const uint32_t sd = pack2(sqrt_apx(__uint_as_float(ve << 16)), sqrt_apx(__uint_as_float(ve & 0xffff0000u)));
            rs[2 * k] = rcp_apx(__uint_as_float(sd << 16)); rs[2 * k + 1] = rcp_apx(__uint_as_float(sd & 0xffff0000u));
        }
        if (rs[0] != 123.f) TSTAMP(13);
        const int ch = tid + UPADF / 8, pch = ch ^ ((ch >> 3) & 1);
#pragma unroll
        for (int c = 0; c < CV_CPB; c++) {
            *reinterpret_cast<uint4*>(Xs + c * XLEN + tid * 8) = xv[c];
            *reinterpret_cast<uint4*>(Us + c * ULEN + pch * 8) =
                make_uint4(ln2(xv[c].x, mw[0], rs[0], rs[1]), ln2(xv[c].y, mw[1], rs[2], rs[3]), ln2(xv[c].z, mw[2], rs[4], rs[5]), ln2(xv[c].w, mw[3], rs[6], rs[7]));
        }
    }
    __syncthreads();
    TSTAMP(1);
#pragma unroll 1
    for (int rd = rd0; rd < (int)rd1; rd++) {
        const int i = 32 * rd + lane;
        if (i < CV_CPB * 193) {
            const int c = i / 193, chunk = i - c * 193 - 1, ch = chunk + UPADF / 8;
            const bf16* uc = Us + c * ULEN;
            const uint4 o = *reinterpret_cast<const uint4*>(uc + (ch ^ ((ch >> 3) & 1)) * 8);
            const uint2 lo = *reinterpret_cast<const uint2*>(uc + ((ch - 1) ^ (((ch - 1) >> 3) & 1)) * 8 + 4);
            const uint2 hi = *reinterpret_cast<const uint2*>(uc + ((ch + 1) ^ (((ch + 1) >> 3) & 1)) * 8);
            const uint32_t w[8] = {lo.x, lo.y, o.x, o.y, o.z, o.w, hi.x, hi.y};
            float v[16], b[8];
#pragma unroll
            for (int k = 0; k < 8; k++) { v[2 * k] = __uint_as_float(w[k] << 16); v[2 * k + 1] = __uint_as_float(w[k] & 0xffff0000u); }
            unsigned char* bx = sm + CV_SM_B + c * BX_LEN + chunk * 16;
#pragma unroll
            for (int k = 0; k < 8; k++) b[k] = v[k + 4] + (v[k + 3] + v[k + 5]);
            *reinterpret_cast<uint2*>(bx + BX_3 + 168) = make_uint2(pack2(b[0], b[1]), pack2(b[2], b[3]));
            *reinterpret_cast<uint2*>(bx + BX_3 + 176) = make_uint2(pack2(b[4], b[5]), pack2(b[6], b[7]));
#pragma unroll
            for (int k = 0; k < 8; k++) b[k] += v[k + 2] + v[k + 6];
            *reinterpret_cast<uint4*>(bx + BX_5 + 160) = make_uint4(pack2(b[0], b[1]), pack2(b[2], b[3]), pack2(b[4], b[5]), pack2(b[6], b[7]));
            if (chunk < 128) {
#pragma unroll
                for (int k = 0; k < 8; k++) b[k] += v[k + 1] + v[k + 7];
                *reinterpret_cast<uint4*>(bx + BX_7 + 272) = make_uint4(pack2(b[0], b[1]), pack2(b[2], b[3]), pack2(b[4], b[5]), pack2(b[6], b[7]));
#pragma unroll
                for (int k = 0; k < 8; k++) b[k] += v[k] + v[k + 8];
                *reinterpret_cast<uint4*>(bx + BX_9 + 272) = make_uint4(pack2(b[0], b[1]), pack2(b[2], b[3]), pack2(b[4], b[5]), pack2(b[6], b[7]));
            }
        }
    }
    __syncwarp();
    if (lane == 0) mbar_arrive(smem_u32(sm + CV_SM_CNT) + 96);
    TSTAMP(2);
    {
        float acc[8][4];
#pragma unroll
        for (int j = 0; j < 8; j++)
#pragma unroll
            for (int k = 0; k < 4; k++) acc[j][k] = 0.f;
#pragma unroll 1
        for (int pass = (type == 2 || type == 4) ? 1 : 0; pass < ((type == 1 || type == 3) ? 1 : 2); pass++) {
            const uint32_t o0 = pass ? lds_off[2] : lds_off[0], o1 = pass ? lds_off[3] : lds_off[1];
            if (H) direct_pass<true>(acc, ubase + T0 * 256, o0, o1, Tc + 64 * pass, pass == 0);
            else direct_pass<false>(acc, ubase, o0, o1, Tc + 64 * pass, pass == 0);
        }
        TSTAMP(6);
        mbar_wait(smem_u32(sm + CV_SM_CNT) + 96, 0);
        if (type != 1 && type != 4) {
            const uint32_t* w2 = reinterpret_cast<const uint32_t*>(sm + CV_SM_T + c * TAPB + TAP_W2) + (115 - 96) + 4 * g - 2 * ti;
            uint32_t f[10][2];
#pragma unroll
            for (int k = 0; k < 10; k++) { f[k][0] = w2[16 * k]; f[k][1] = w2[16 * k - 8]; }
            const uint32_t ab = bbase + off2 + (2 * T0 + 6) * 128;
            const int kmax = H ? 23 : 8;
            uint32_t a[3][4];
            ldsm_x4_t(a[0], ab);
            ldsm_x4_t(a[1], ab - 128);
#pragma unroll
            for (int kp = 0; kp < 24; kp++) {
                if (kp > kmax) break;
                if (kp < 22) ldsm_x4_t(a[(kp + 2) % 3], ab - min(kp + 2, kmax) * 128);
#pragma unroll
                for (int j = 0; j < 8; j++) {
                    const int ee = 2 * j - 14 + kp;
                    if (ee >= 0 && ee <= 9) mma_bf16(acc[j], a[kp % 3][0], a[kp % 3][1], a[kp % 3][2], a[kp % 3][3], f[ee][0], f[ee][1]);
                }
            }
        }
        TSTAMP(7);
        if (type != 2 && type != 4) {
            const uint32_t* w3 = reinterpret_cast<const uint32_t*>(sm + CV_SM_T + c * TAPB + TAP_W3) + (129 - 96) + 2 * (g - ti);
            uint32_t f[9][2];
#pragma unroll
            for (int k = 0; k < 9; k++) { f[k][0] = w3[16 * k]; f[k][1] = w3[16 * k - 8]; }
            const uint32_t ab = bbase + off3 + (T0 - 2) * 256;
            uint32_t a[3][4];
            ldsm_x4_t(a[0], ab);
            ldsm_x4_t(a[1], ab - H * 256);
#pragma unroll
            for (int kp = 0; kp < 9; kp++) {
                if (kp > T0) break;
                if (kp < 7) ldsm_x4_t(a[(kp + 2) % 3], ab - min(kp + 2, T0) * 256);
#pragma unroll
                for (int j = 0; j < 8; j++) {
                    const int dl = j - 7 + kp;
                    if (dl >= 0 && dl <= 8) mma_bf16(acc[j], a[kp % 3][0], a[kp % 3][1], a[kp % 3][2], a[kp % 3][3], f[dl][0], f[dl][1]);
                }
            }
            const uint2* Dc = reinterpret_cast<const uint2*>(sm + CV_SM_T + c * TAPB + TAP_C) + e;
            const uint2 h63 = Dc[16], h64 = Dc[32], l63 = Dc[8], l64 = Dc[24];
#pragma unroll
            for (int j = 0; j < 8; j++)
                if (j == 7 || H) {
                    uint32_t bq[4];
                    ldsm_x4(bq, ubase + offc + (T0 + j - 8) * 256);
                    mma_bf16(acc[j], h64.x, h64.y, l64.x, l64.y, bq[0], bq[1]);
                    mma_bf16(acc[j], h63.x, h63.y, l63.x, l63.y, bq[2], bq[3]);
                }
        }
        TSTAMP(8);
        const bool hi_half = (type == 2 || type == 4);
        if (type != 0) {
            const int pair = H ? c : 5;
            float4* give = reinterpret_cast<float4*>(sm + CV_SM_P + pair * 4096 + (hi_half ? 2048 : 0)) + lane;
            const float4* take = reinterpret_cast<const float4*>(sm + CV_SM_P + pair * 4096 + (hi_half ? 0 : 2048)) + lane;
            const uint32_t pb = smem_u32(sm + CV_SM_CNT) + pair * 16;
#pragma unroll
            for (int j = 0; j < 4; j++)
                give[32 * j] = hi_half ? make_float4(acc[j][0], acc[j][1], acc[j][2], acc[j][3]) : make_float4(acc[j + 4][0], acc[j + 4][1], acc[j + 4][2], acc[j + 4][3]);
            __syncwarp();
            if (lane == 0) mbar_arrive(pb + (hi_half ? 8 : 0));
            mbar_wait(pb + (hi_half ? 0 : 8), 0);
#pragma unroll
            for (int j = 0; j < 4; j++) {
                const float4 v = take[32 * j];
                acc[j][0] = (hi_half ? acc[j + 4][0] : acc[j][0]) + v.x; acc[j][1] = (hi_half ? acc[j + 4][1] : acc[j][1]) + v.y;
                acc[j][2] = (hi_half ? acc[j + 4][2] : acc[j][2]) + v.z; acc[j][3] = (hi_half ? acc[j + 4][3] : acc[j][3]) + v.w;
            }
        }
        const uint32_t dk = __shfl_sync(~0u, (uint32_t)dskr, c) * 0x10001u;
#pragma unroll 1
        for (int rnd = 0; rnd < (type == 0 ? 2 : 1); rnd++) {
            const int Q = 2 * H + (hi_half ? 1 : rnd);
            if (rnd) {
#pragma unroll
                for (int j = 0; j < 4; j++)
#pragma unroll
                    for (int k = 0; k < 4; k++) acc[j][k] = acc[j + 4][k];
            }
            const uint32_t ya = smem_u32(Ys + c * XLEN) + (128 * (4 * Q + (lane >> 4)) + 16 * (lane & 7) + 8 * ((lane >> 3) & 1)) * 2;
#pragma unroll
            for (int j = 0; j < 4; j += 2)
                asm volatile("stmatrix.sync.aligned.m8n8.x4.trans.shared.b16 [%0], {%1,%2,%3,%4};" ::"r"(ya + j * 256),
                             "r"(pack2(acc[j][0], acc[j][1])), "r"(pack2(acc[j][2], acc[j][3])),
                             "r"(pack2(acc[j + 1][0], acc[j + 1][1])), "r"(pack2(acc[j + 1][2], acc[j + 1][3])) : "memory");
            __syncwarp();
            uint4 yv[2], xv[2], uv[2];
#pragma unroll
            for (int k = 0; k < 2; k++) {
                const int t = 512 * Q + 256 * k + 8 * lane, cu = (t + UPADF) >> 3;
                yv[k] = *reinterpret_cast<const uint4*>(Ys + c * XLEN + t);
                xv[k] = *reinterpret_cast<const uint4*>(Xs + c * XLEN + t);
                uv[k] = *reinterpret_cast<const uint4*>(Us + c * ULEN + (cu ^ ((cu >> 3) & 1)) * 8);
            }
#pragma unroll
            for (int k = 0; k < 2; k++)
                asm volatile("st.relaxed.gpu.global.v4.u32 [%0], {%1,%2,%3,%4};" ::"l"((layer ? g_yT : g_xcT) + (size_t)(d0 + c) * XCP + 512 * Q + 256 * k + 8 * lane),
                             "r"(fin2(xv[k].x, yv[k].x, uv[k].x, dk)), "r"(fin2(xv[k].y, yv[k].y, uv[k].y, dk)), "r"(fin2(xv[k].z, yv[k].z, uv[k].z, dk)), "r"(fin2(xv[k].w, yv[k].w, uv[k].w, dk)) : "memory");
        }
        TSTAMP(4);
        if (layer == 1) {
            const int mb = blockIdx.x >> 3, cg = blockIdx.x & 7;
            const bf16* src = g_yT + (size_t)(cg * 80 + (tid >> 4)) * XCP + mb * 128 + (tid & 15) * 8;
            uint32_t v[3][4];
            __syncthreads();
            TSTAMP(5);
            uint32_t todo = warp < 8 ? 7 : 3;
#pragma unroll 1
            for (int it = 0; it < SPIN_MAX; it++) {
#pragma unroll
                for (int k = 0; k < 3; k++)
                    if (todo >> k & 1)
                        asm volatile("ld.relaxed.gpu.global.v4.u32 {%0,%1,%2,%3}, [%4];" : "=r"(v[k][0]), "=r"(v[k][1]), "=r"(v[k][2]), "=r"(v[k][3]) : "l"(src + k * (32 * XCP)) : "memory");
#pragma unroll
                for (int k = 0; k < 3; k++)
                    if ((todo >> k & 1) && v[k][0] != ~0u && v[k][1] != ~0u && v[k][2] != ~0u && v[k][3] != ~0u) {
                        *reinterpret_cast<uint4*>(sm + (32 * k + (tid >> 4)) * 272 + (tid & 15) * 16) = make_uint4(v[k][0], v[k][1], v[k][2], v[k][3]);
                        todo ^= 1u << k;
                    }
                if (!todo) break;
                __nanosleep(CV_SLEEP);
            }
            __syncthreads();
            uint32_t w[12];
#pragma unroll
            for (int k = 0; k < 3; k++) ldsm_x4(&w[4 * k], smem_u32(sm) + min(32 * k + lane, 79) * 272 + warp * 16);
            const uint32_t ot = smem_u32(sm + CV_SM_O) + warp * 1280, oa = ot + (lane & 7) * 160 + (lane >> 3) * 16;
            stsm_x4_t(oa, w[0], w[1], w[2], w[3]);
            stsm_x4_t(oa + 64, w[4], w[5], w[6], w[7]);
            asm volatile("stmatrix.sync.aligned.m8n8.x2.trans.shared.b16 [%0], {%1,%2};" ::"r"(oa + 128), "r"(w[8]), "r"(w[9]) : "memory");
            fence_async_smem();
            __syncwarp();
            if (lane == 0) tma_store_2d(&tmOut, cg * 80, mb * 128 + 8 * warp, ot);
        }
    }
    TSTAMP(3);
    GSTAMP(g_tim, 14);
    SPAN(3 + 4 * layer, 3);
}

__device__ __forceinline__ void wgmma_fence() { asm volatile("wgmma.fence.sync.aligned;" ::: "memory"); }
__device__ __forceinline__ void wgmma_commit() { asm volatile("wgmma.commit_group.sync.aligned;" ::: "memory"); }
template <int N> __device__ __forceinline__ void wgmma_wait() { asm volatile("wgmma.wait_group.sync.aligned %0;" ::"n"(N) : "memory"); }
__device__ __forceinline__ uint64_t make_desc(uint32_t addr, uint32_t lbo, uint32_t sbo, uint32_t mode) {
    return (uint64_t)((addr & 0x3FFFF) >> 4) | ((uint64_t)(lbo >> 4) << 16) | ((uint64_t)(sbo >> 4) << 32) | ((uint64_t)mode << 62);
}
template <int TA, int TB>
__device__ __forceinline__ void wgmma_n240(float (&d)[120], uint64_t da, uint64_t db, int acc) {
    asm volatile("{\n.reg .pred p;\nsetp.ne.b32 p, %124, 0;\nwgmma.mma_async.sync.aligned.m64n240k16.f32.bf16.bf16 {%0,%1,%2,%3,%4,%5,%6,%7,%8,%9,%10,%11,%12,%13,%14,%15,%16,%17,%18,%19,%20,%21,%22,%23,%24,%25,%26,%27,%28,%29,%30,%31,%32,%33,%34,%35,%36,%37,%38,%39,%40,%41,%42,%43,%44,%45,%46,%47,%48,%49,%50,%51,%52,%53,%54,%55,%56,%57,%58,%59,%60,%61,%62,%63,%64,%65,%66,%67,%68,%69,%70,%71,%72,%73,%74,%75,%76,%77,%78,%79,%80,%81,%82,%83,%84,%85,%86,%87,%88,%89,%90,%91,%92,%93,%94,%95,%96,%97,%98,%99,%100,%101,%102,%103,%104,%105,%106,%107,%108,%109,%110,%111,%112,%113,%114,%115,%116,%117,%118,%119}, %120, %121, p, 1, 1, %122, %123;\n}"
                 : "+f"(d[0]), "+f"(d[1]), "+f"(d[2]), "+f"(d[3]), "+f"(d[4]), "+f"(d[5]), "+f"(d[6]), "+f"(d[7]), "+f"(d[8]), "+f"(d[9]), "+f"(d[10]), "+f"(d[11]), "+f"(d[12]), "+f"(d[13]), "+f"(d[14]), "+f"(d[15]), "+f"(d[16]), "+f"(d[17]), "+f"(d[18]), "+f"(d[19]), "+f"(d[20]), "+f"(d[21]), "+f"(d[22]), "+f"(d[23]), "+f"(d[24]), "+f"(d[25]), "+f"(d[26]), "+f"(d[27]), "+f"(d[28]), "+f"(d[29]), "+f"(d[30]), "+f"(d[31]), "+f"(d[32]), "+f"(d[33]), "+f"(d[34]), "+f"(d[35]), "+f"(d[36]), "+f"(d[37]), "+f"(d[38]), "+f"(d[39]), "+f"(d[40]), "+f"(d[41]), "+f"(d[42]), "+f"(d[43]), "+f"(d[44]), "+f"(d[45]), "+f"(d[46]), "+f"(d[47]), "+f"(d[48]), "+f"(d[49]), "+f"(d[50]), "+f"(d[51]), "+f"(d[52]), "+f"(d[53]), "+f"(d[54]), "+f"(d[55]), "+f"(d[56]), "+f"(d[57]), "+f"(d[58]), "+f"(d[59]), "+f"(d[60]), "+f"(d[61]), "+f"(d[62]), "+f"(d[63]), "+f"(d[64]), "+f"(d[65]), "+f"(d[66]), "+f"(d[67]), "+f"(d[68]), "+f"(d[69]), "+f"(d[70]), "+f"(d[71]), "+f"(d[72]), "+f"(d[73]), "+f"(d[74]), "+f"(d[75]), "+f"(d[76]), "+f"(d[77]), "+f"(d[78]), "+f"(d[79]), "+f"(d[80]), "+f"(d[81]), "+f"(d[82]), "+f"(d[83]), "+f"(d[84]), "+f"(d[85]), "+f"(d[86]), "+f"(d[87]), "+f"(d[88]), "+f"(d[89]), "+f"(d[90]), "+f"(d[91]), "+f"(d[92]), "+f"(d[93]), "+f"(d[94]), "+f"(d[95]), "+f"(d[96]), "+f"(d[97]), "+f"(d[98]), "+f"(d[99]), "+f"(d[100]), "+f"(d[101]), "+f"(d[102]), "+f"(d[103]), "+f"(d[104]), "+f"(d[105]), "+f"(d[106]), "+f"(d[107]), "+f"(d[108]), "+f"(d[109]), "+f"(d[110]), "+f"(d[111]), "+f"(d[112]), "+f"(d[113]), "+f"(d[114]), "+f"(d[115]), "+f"(d[116]), "+f"(d[117]), "+f"(d[118]), "+f"(d[119])
                 : "l"(da), "l"(db), "n"(TA), "n"(TB), "r"(acc));
}

template <int TA, int TB>
__device__ __forceinline__ void wgmma_n80(float (&d)[40], uint64_t da, uint64_t db, int acc) {
    asm volatile("{\n.reg .pred p;\nsetp.ne.b32 p, %44, 0;\nwgmma.mma_async.sync.aligned.m64n80k16.f32.bf16.bf16 {%0,%1,%2,%3,%4,%5,%6,%7,%8,%9,%10,%11,%12,%13,%14,%15,%16,%17,%18,%19,%20,%21,%22,%23,%24,%25,%26,%27,%28,%29,%30,%31,%32,%33,%34,%35,%36,%37,%38,%39}, %40, %41, p, 1, 1, %42, %43;\n}"
                 : "+f"(d[0]), "+f"(d[1]), "+f"(d[2]), "+f"(d[3]), "+f"(d[4]), "+f"(d[5]), "+f"(d[6]), "+f"(d[7]), "+f"(d[8]), "+f"(d[9]), "+f"(d[10]), "+f"(d[11]), "+f"(d[12]), "+f"(d[13]), "+f"(d[14]), "+f"(d[15]), "+f"(d[16]), "+f"(d[17]), "+f"(d[18]), "+f"(d[19]), "+f"(d[20]), "+f"(d[21]), "+f"(d[22]), "+f"(d[23]), "+f"(d[24]), "+f"(d[25]), "+f"(d[26]), "+f"(d[27]), "+f"(d[28]), "+f"(d[29]), "+f"(d[30]), "+f"(d[31]), "+f"(d[32]), "+f"(d[33]), "+f"(d[34]), "+f"(d[35]), "+f"(d[36]), "+f"(d[37]), "+f"(d[38]), "+f"(d[39])
                 : "l"(da), "l"(db), "n"(TA), "n"(TB), "r"(acc));
}

constexpr int A1_THREADS = 384;
constexpr int A1_NST = 4;
#define A1_PRE0 2
#define A1_SKEW 8
#define A1_PRE1 1
constexpr int A1_STAGE = 16384 + WQ_STAGE;
constexpr int A1_KVP = 336;
constexpr int A1_SM_KV = 2 * A1_STAGE;
constexpr int A1_SM_O = A1_SM_KV + 144 * A1_KVP;
constexpr int A1_SM_BAR = A1_NST * A1_STAGE;
constexpr int A1_SM_CS = A1_SM_BAR + 256;
constexpr int A1_SM_RS = A1_SM_CS + 1024;
constexpr int A1_SMEM = A1_SM_RS + 1024 + 1024;
static_assert(A1_SM_O % 128 == 0 && A1_SM_O + 20480 <= A1_SM_BAR, "layout");

template <int L>
__device__ __forceinline__ void a1_mainloop(float (&acc)[120], uint32_t sbase, uint32_t bars, int wg, int tile) {
    constexpr int layer = L; (void)layer;
    const uint64_t da0 = L ? make_desc(sbase + wg * 8192, 8192, 1024, 1) : make_desc(sbase + wg * 8192, 16, 1024, 1), db0 = make_desc(sbase + 16384, 16, 1024, 1);
#pragma unroll 1
    for (int t = 0; t < 10; t++) {
        const int st = t % A1_NST;
        mbar_wait(bars + 8 * st, (t / A1_NST) & 1);
        if (t == A1_SKEW && wg == 0) mbar_wait(bars + 160, 0);
        TSTAMP3(1 + t);
        wgmma_fence();
#pragma unroll
        for (int kk = 0; kk < 4; kk++) wgmma_n240<L, 0>(acc, da0 + (uint32_t)(st * (A1_STAGE / 16) + kk * (L ? 128 : 2)), db0 + (uint32_t)(st * (A1_STAGE / 16) + kk * 2), kk ? 1 : t);
        wgmma_commit();
        if (t == 9 && threadIdx.x == 128) { mbar_arrive(bars + 160); mbar_arrive(bars + 144); }
        if (t == A1_SKEW - 1 && wg == 0) wgmma_wait<0>(); else wgmma_wait<1>();
        if (t > 0 && t < 9 && (threadIdx.x & 127) == 0) {
            if (t != A1_SKEW || wg) mbar_arrive(bars + 8 * (A1_NST + (t - 1) % A1_NST));
            if (t == A1_SKEW - 1 && wg == 0) mbar_arrive(bars + 8 * (A1_NST + t % A1_NST));
        }
    }
}

__global__ void __launch_bounds__(A1_THREADS, 1) a1_kernel(const int layer, const bf16* __restrict__ x0, const unsigned char* __restrict__ wq, const __grid_constant__ CUtensorMap tmX,
                                                           const __grid_constant__ CUtensorMap tmOst) {
    extern __shared__ unsigned char smraw[];
    const uint32_t sbase = (smem_u32(smraw) + 1023) & ~1023u;
    const uint32_t bars = sbase + A1_SM_BAR;
    const uint32_t bar_stat = bars + 64, bar_kv = bars + 72, bar_rd = bars + 168;
    const int tid = threadIdx.x, w = __shfl_sync(~0u, tid >> 5, 0), wg = w >> 2;
    const int tile = sm_tile();
    if (tile >= 128) { sm_idle(2 * layer); return; }
    const int mb = (tile >> 2) & 15, hg = 4 * (tile >> 6) + (tile & 3);
    unsigned char* stg = smraw + (sbase - smem_u32(smraw));
    float* cs = reinterpret_cast<float*>(stg + A1_SM_CS);
    float2* rst = reinterpret_cast<float2*>(stg + A1_SM_RS);
    const int pre = layer ? A1_PRE1 : A1_PRE0;
    auto issue_w = [&](int it) {
        const int kb = it + 5 * (hg >> 2) - (it + 5 * (hg >> 2) >= 10 ? 10 : 0);
        bulk_load(sbase + (it % A1_NST) * A1_STAGE + 16384, wq + (hg * 10 + kb) * WQ_STAGE, WQ_STAGE, bars + 8 * (it % A1_NST));
    };
    auto issue_x = [&](int it) {
        const int kb = it + 5 * (hg >> 2) - (it + 5 * (hg >> 2) >= 10 ? 10 : 0);
        const uint32_t dst = sbase + (it % A1_NST) * A1_STAGE, full = bars + 8 * (it % A1_NST);
        tma_load_3d(dst, &tmX, layer ? 0 : kb * 64, layer ? kb * 64 : 0, mb * 2, full);
    };
    if (w == 8) {
        if (tid == 256) {
            prefetch_tmap(&tmX);
#pragma unroll
            for (int i = 0; i < A1_NST; i++) { mbar_init(bars + 8 * i, 1); mbar_init(bars + 8 * (A1_NST + i), 2); }
            asm volatile("fence.mbarrier_init.release.cluster;" ::: "memory");
#pragma unroll
            for (int i = 0; i < A1_NST; i++) mbar_expect_tx(bars + 8 * i, A1_STAGE);
        }
        __syncwarp();
        asm volatile("bar.arrive 0, 384;" ::: "memory");
        if (tid == 256) {
#pragma unroll 1
            for (int kb = 0; kb < pre; kb++) { if (layer) issue_w(kb); else issue_x(kb); }
            pdl_sync();
#pragma unroll 1
            for (int kb = 0; kb < A1_NST; kb++) {
                if (kb >= pre || layer) issue_x(kb);
                if (kb >= pre || !layer) issue_w(kb);
            }
        }
    } else {
        if (tid == 0) {
            mbar_init(bar_stat, 3);
#pragma unroll
            for (int i = 0; i < 9; i++) mbar_init(bar_kv + 8 * i, i ? 1 : 4);
            mbar_init(bars + 144, 1);
            mbar_init(bars + 160, 1);
#pragma unroll
            for (int i = 0; i < 5; i++) mbar_init(bar_rd + 8 * i, 2);
            asm volatile("fence.mbarrier_init.release.cluster;" ::: "memory");
        } else if (tid == 320) prefetch_tmap(&tmOst);
        asm volatile("bar.sync 0, 384;" ::: "memory");
    }
    SPAN(1 + 4 * layer, 0);
    constexpr int on = 1;
    if (wg == 2) {
        if (w == 9) {
            if (layer == 0) pdl_sync();
            float4 a[2] = {};
#pragma unroll
            for (int k = 0; k < 10; k++)
#pragma unroll
                for (int h = 0; h < 2; h++) {
                    const float4 v = __ldcg(reinterpret_cast<const float4*>(g_csp + k * 1920 + hg * 240) + min(tid - 288 + 32 * h, 59));
                    a[h].x += v.x; a[h].y += v.y; a[h].z += v.z; a[h].w += v.w;
                }
            reinterpret_cast<float4*>(cs)[tid - 288] = a[0];
            reinterpret_cast<float4*>(cs)[min(tid - 256, 59)] = a[1];
            __syncwarp();
            if (tid == 288) mbar_arrive(bar_stat);
        } else if (w == 8) {
            if (tid == 256) {
#pragma unroll 1
                for (int kb = A1_NST; kb < 10; kb++) {
                    mbar_wait(bars + 8 * (A1_NST + kb % A1_NST), ((kb / A1_NST) - 1) & 1);
                    if (layer && kb < 9) mbar_wait(bar_rd + 8 * (kb - A1_NST), 0);
                    mbar_expect_tx(bars + 8 * (kb % A1_NST), A1_STAGE);
                    issue_x(kb); issue_w(kb);
                }
                TSTAMP1T(6, 256);
            }
            __syncwarp();
        } else {
            const int j = tid - 320;
            const uint32_t tag = ld_epoch();
            if (tid == 352) sm_started(2 * layer);
            if (layer == 0) {
                const uint4* src = reinterpret_cast<const uint4*>(x0 + (size_t)(mb * 128 + hg * 16 + (j >> 2)) * DM);
                uint4 v[20];
#pragma unroll
                for (int k = 0; k < 20; k++) v[k] = __ldg(src + (j & 3) + 4 * k);
                const float p0 = __uint_as_float(__shfl_sync(~0u, v[0].x, j & 28) << 16);
                float s[2] = {0.f, 0.f}, q[2] = {0.f, 0.f};
#pragma unroll
                for (int k = 0; k < 20; k++) {
                    const uint32_t w[4] = {v[k].x, v[k].y, v[k].z, v[k].w};
#pragma unroll
                    for (int i = 0; i < 4; i++) {
                        const float a = __uint_as_float(w[i] << 16) - p0, b = __uint_as_float(w[i] & 0xffff0000u) - p0;
                        s[0] += a; s[1] += b; q[0] = fmaf(a, a, q[0]); q[1] = fmaf(b, b, q[1]);
                    }
                }
                float s0 = s[0] + s[1], q0 = q[0] + q[1];
#pragma unroll
                for (int o = 1; o <= 2; o <<= 1) { s0 += __shfl_xor_sync(~0u, s0, o); q0 += __shfl_xor_sync(~0u, q0, o); }
                if ((j & 3) == 0) {
                    const float d = s0 * (1.0f / DM);
                    const uint32_t ms = pack2(p0 + d, sqrt_apx(rbf(rbf(fmaxf(fmaf(-d, d, q0 * (1.0f / DM)), 0.f)) + 1e-5f)));
                    asm volatile("st.global.cg.u64 [%0], %1;" ::"l"(g_rstat + mb * 128 + hg * 16 + (j >> 2)), "l"(tagw(ms, tag)) : "memory");
                    g_piv[mb * 128 + hg * 16 + (j >> 2)] = __ushort_as_bfloat16((unsigned short)ms);
                }
            }
            if (layer == 0) {
                ulonglong2 v;
#pragma unroll 1
                for (int it = 0; it < SPIN_MAX; it++) {
                    v = ld_tag2(reinterpret_cast<const ulonglong2*>(g_rstat + mb * 128) + j);
                    if (tag_ok(v, tag)) break;
                    __nanosleep(100);
                }
                *reinterpret_cast<float4*>(rst + 2 * j) = make_float4(__uint_as_float((uint32_t)v.x << 16), rcp_apx(__uint_as_float((uint32_t)v.x & 0xffff0000u)),
                                                                      __uint_as_float((uint32_t)v.y << 16), rcp_apx(__uint_as_float((uint32_t)v.y & 0xffff0000u)));
            } else {
                const int ch = j & 7, kg = (j >> 3) & 3;
                const unsigned char* src = stg + (j >> 5) * 8192 + (hg & 3) * 2048;
                uint4 v[20], pv;
#pragma unroll
                for (int it = 0; it < 5; it++) {
                    mbar_wait(bars + 8 * (it % A1_NST), it / A1_NST);
#pragma unroll
                    for (int k = 0; k < 4; k++) v[4 * it + k] = *reinterpret_cast<const uint4*>(src + (it % A1_NST) * A1_STAGE + (4 * k + kg) * 128 + ((ch ^ ((4 * k + kg) & 7)) << 4));
                    if (it == 0) pv = *reinterpret_cast<const uint4*>(src + (ch << 4));
                    asm volatile("" :: "r"(v[4 * it].x), "r"(v[4 * it + 1].x), "r"(v[4 * it + 2].x), "r"(v[4 * it + 3].x), "r"(pv.x) : "memory");
                    __syncwarp();
                    if ((tid & 31) == 0) mbar_arrive(bar_rd + 8 * it);
                }
                float s[8], q[8], p0[8] = {__uint_as_float(pv.x << 16), __uint_as_float(pv.x & 0xffff0000u), __uint_as_float(pv.y << 16), __uint_as_float(pv.y & 0xffff0000u),
                                           __uint_as_float(pv.z << 16), __uint_as_float(pv.z & 0xffff0000u), __uint_as_float(pv.w << 16), __uint_as_float(pv.w & 0xffff0000u)};
#pragma unroll
                for (int i = 0; i < 8; i++) { s[i] = 0.f; q[i] = 0.f; }
#pragma unroll
                for (int k = 0; k < 20; k++) {
                    const uint32_t w[4] = {v[k].x, v[k].y, v[k].z, v[k].w};
#pragma unroll
                    for (int i = 0; i < 4; i++) {
                        const float a = __uint_as_float(w[i] << 16) - p0[2 * i], b = __uint_as_float(w[i] & 0xffff0000u) - p0[2 * i + 1];
                        s[2 * i] += a; s[2 * i + 1] += b; q[2 * i] = fmaf(a, a, q[2 * i]); q[2 * i + 1] = fmaf(b, b, q[2 * i + 1]);
                    }
                }
#pragma unroll
                for (int i = 0; i < 4; i++) {
                    const bool up = kg & 2;
                    const float ss = __shfl_xor_sync(~0u, up ? s[i] : s[i + 4], 16), qq = __shfl_xor_sync(~0u, up ? q[i] : q[i + 4], 16);
                    s[i] = (up ? s[i + 4] : s[i]) + ss; q[i] = (up ? q[i + 4] : q[i]) + qq; p0[i] = up ? p0[i + 4] : p0[i];
                }
#pragma unroll
                for (int i = 0; i < 2; i++) {
                    const bool up = kg & 1;
                    const float ss = __shfl_xor_sync(~0u, up ? s[i] : s[i + 2], 8), qq = __shfl_xor_sync(~0u, up ? q[i] : q[i + 2], 8);
                    s[i] = (up ? s[i + 2] : s[i]) + ss; q[i] = (up ? q[i + 2] : q[i]) + qq; p0[i] = up ? p0[i + 2] : p0[i];
                }
#pragma unroll
                for (int r = 0; r < 2; r++) {
                    const float d = s[r] * (1.0f / 80.0f);
                    st_tag2(g_part + (mb * 8 + hg) * 128 + 64 * r + j, __float_as_uint(p0[r] + d), __float_as_uint(fmaxf(fmaf(-d, s[r], q[r]), 0.f)), tag);
                }
                const ulonglong2* gp = g_part + mb * 8 * 128 + j;
#pragma unroll 1
                for (int it = 0; it < SPIN_MAX; it++) {
                    if (__all_sync(~0u, tag_ok(ld_tag2(gp + (j & 7) * 128 + 64), tag))) break;
                    __nanosleep(200);
                }
                ulonglong2 pw[16];
#pragma unroll 1
                for (int it = 0; it < SPIN_MAX; it++) {
                    bool ok = true;
#pragma unroll
                    for (int k = 0; k < 16; k++) pw[k] = ld_tag2(gp + k * 64);
#pragma unroll
                    for (int k = 0; k < 16; k++) ok = ok && tag_ok(pw[k], tag);
                    if (ok) break;
                    __nanosleep(200);
                }
                float o[4];
#pragma unroll
                for (int r = 0; r < 2; r++) {
                    float mean = 0.f, m2 = 0.f;
#pragma unroll
                    for (int k = 0; k < 8; k++) mean += __uint_as_float((uint32_t)pw[2 * k + r].x);
                    mean *= 0.125f;
#pragma unroll
                    for (int k = 0; k < 8; k++) {
                        const float dm = __uint_as_float((uint32_t)pw[2 * k + r].x) - mean;
                        m2 += fmaf(80.0f * dm, dm, __uint_as_float((uint32_t)pw[2 * k + r].y));
                    }
                    o[2 * r] = rbf(mean);
                    o[2 * r + 1] = rcp_apx(rbf(sqrt_apx(rbf(rbf(m2 * (1.0f / DM)) + 1e-5f))));
                }
                const int row = (j >> 5) * 64 + (j & 7) * 8 + ((j >> 3) & 3) * 2;
                *reinterpret_cast<float4*>(rst + row) = make_float4(o[0], o[1], o[2], o[3]);
                if (hg == 0) *reinterpret_cast<uint32_t*>(g_piv + SEQ + mb * 128 + row) = __byte_perm(__float_as_uint(o[0]), __float_as_uint(o[2]), 0x7632);
            }
            TSTAMP1T(7, 320);
            __syncwarp();
            if ((tid & 31) == 0) mbar_arrive(bar_stat);
        }
    } else {
        float acc[120];
        const int lane = tid & 31, warp = w & 7, g = lane >> 2, t = lane & 3;
        if (on) {
            SPAN(1 + 4 * layer, 1);
            TSTAMP1(0);
            if (threadIdx.x == 0) { GSTAMP(g_tim1, 15); }
            TSTAMP3(0);
            if (layer == 0) a1_mainloop<0>(acc, sbase, bars, wg, tile); else a1_mainloop<1>(acc, sbase, bars, wg, tile);
            mbar_wait(bar_stat, 0);
            mbar_wait(bars + 8 * (A1_NST + 3), 1);
            wgmma_wait<0>();
        }
        const float2 sa_ = rst[16 * warp + g], sb_ = rst[16 * warp + g + 8];
        TSTAMP1(2);
        TSTAMP1T(13, 224);
        uint32_t f[30][2];
        auto norm = [&](int j0) {
            float2 cc[10];
#pragma unroll
            for (int j = 0; j < 10; j++) cc[j] = *reinterpret_cast<const float2*>(cs + 8 * (j0 + j) + 2 * t);
#pragma unroll
            for (int j = 0; j < 10; j++) {
                const float* a = acc + 4 * (j0 + j);
                f[j0 + j][0] = pack2(fmaf(-sa_.x, cc[j].x, a[0]) * sa_.y, fmaf(-sa_.x, cc[j].y, a[1]) * sa_.y);
                f[j0 + j][1] = pack2(fmaf(-sb_.x, cc[j].x, a[2]) * sb_.y, fmaf(-sb_.x, cc[j].y, a[3]) * sb_.y);
            }
        };
        norm(10); norm(20);
        if (warp == 7) {
            uint4* hout = g_halo + ((layer * 16 + mb) * 8 + hg) * 320 + lane;
#pragma unroll
            for (int j = 0; j < 20; j += 2)
                asm volatile("st.relaxed.gpu.global.v4.u32 [%0], {%1,%2,%3,%4};" ::"l"(hout + 16 * j), "r"(f[10 + j][0]), "r"(f[10 + j][1]), "r"(f[11 + j][0]), "r"(f[11 + j][1]) : "memory");
        }
        TSTAMP1T(12, 224);
        const uint32_t kvw = sbase + A1_SM_KV + 16 * warp * A1_KVP;
        const uint32_t mrow = kvw + (lane & 15) * A1_KVP + (lane >> 4) * 16;
#pragma unroll
        for (int j = 0; j < 20; j += 2) stsm_x4(mrow + 16 * A1_KVP + 16 * j, f[10 + j][0], f[10 + j][1], f[11 + j][0], f[11 + j][1]);
        __syncwarp();
        if (lane == 0 && on) mbar_arrive(bar_kv + 8 * (warp + 1));
        norm(0);
        TSTAMP1T(10, 64);
        float sc[4][4][4];
        uint32_t qs[4][2];
#pragma unroll
        for (int h = 0; h < 4; h++) {
            const int jb = 5 * (h >> 1) + 3 * (h & 1), js = 5 * (h >> 1) + 2;
            qs[h][0] = (t >> 1) == (h & 1) ? f[js][0] : 0u; qs[h][1] = (t >> 1) == (h & 1) ? f[js][1] : 0u;
#pragma unroll
            for (int nt = 2; nt < 4; nt++) {
#pragma unroll
                for (int e = 0; e < 4; e++) sc[h][nt][e] = 0.f;
                mma_bf16(sc[h][nt], f[jb][0], f[jb][1], f[jb + 1][0], f[jb + 1][1], f[10 + jb][nt - 2], f[11 + jb][nt - 2]);
                mma_bf16_k8(sc[h][nt], qs[h][0], qs[h][1], f[10 + js][nt - 2]);
            }
        }
        if (on) mbar_wait(bar_kv + 8 * warp, 0);
        TSTAMP1(8);
        uint32_t kp[10][2];
#pragma unroll
        for (int j = 0; j < 10; j += 2) ldsm_x4(&kp[j][0], mrow + 16 * j);
#pragma unroll
        for (int h = 0; h < 4; h++) {
            const int jb = 5 * (h >> 1) + 3 * (h & 1), js = 5 * (h >> 1) + 2;
#pragma unroll
            for (int nt = 0; nt < 2; nt++) {
#pragma unroll
                for (int e = 0; e < 4; e++) sc[h][nt][e] = 0.f;
                mma_bf16(sc[h][nt], f[jb][0], f[jb][1], f[jb + 1][0], f[jb + 1][1], kp[jb][nt], kp[jb + 1][nt]);
                mma_bf16_k8(sc[h][nt], qs[h][0], qs[h][1], kp[js][nt]);
            }
        }
        uint32_t vb[10][4];
#pragma unroll
        for (int j = 0; j < 10; j++) ldsm_x4_t(vb[j], kvw + lane * A1_KVP + 160 + 16 * j);
        TSTAMP1T(3, 64);
        const bool odd = g & 1, hi = t > (g >> 1), edge = (mb | warp) == 0;
        float p[4][4], mx[4][2], sum[4][2];
#pragma unroll
        for (int h = 0; h < 4; h++) {
#pragma unroll
            for (int r = 0; r < 2; r++) {
                const float a = odd ? sc[h][1 + r][2 * r + 1] : sc[h][1 + r][2 * r];
                const float b0 = odd ? sc[h][r][2 * r + 1] : sc[h][r][2 * r], b1 = odd ? sc[h][2 + r][2 * r + 1] : sc[h][2 + r][2 * r];
                const uint32_t w1 = pack2(a, hi ? b0 : b1);
                const uint32_t w2 = pack2(__uint_as_float(w1 << 16) * 0.22360679774997896f, __uint_as_float(w1 & 0xffff0000u) * 0.22360679774997896f);
                p[h][2 * r] = __uint_as_float(w2 << 16); p[h][2 * r + 1] = __uint_as_float(w2 & 0xffff0000u);
            }
            if (edge) {
                p[h][0] = -1.0e9f;
                if (hi) { p[h][1] = -1.0e9f; p[h][3] = -1.0e9f; }
            }
            mx[h][0] = fmaxf(p[h][0], p[h][1]); mx[h][1] = fmaxf(p[h][2], p[h][3]);
        }
#pragma unroll
        for (int o = 1; o <= 2; o <<= 1)
#pragma unroll
            for (int h = 0; h < 4; h++)
#pragma unroll
                for (int r = 0; r < 2; r++) mx[h][r] = fmaxf(mx[h][r], __shfl_xor_sync(~0u, mx[h][r], o));
#pragma unroll
        for (int h = 0; h < 4; h++)
#pragma unroll
            for (int r = 0; r < 2; r++) {
                p[h][2 * r] = __expf(p[h][2 * r] - mx[h][r]); p[h][2 * r + 1] = __expf(p[h][2 * r + 1] - mx[h][r]);
                sum[h][r] = p[h][2 * r] + p[h][2 * r + 1];
            }
#pragma unroll
        for (int o = 1; o <= 2; o <<= 1)
#pragma unroll
            for (int h = 0; h < 4; h++)
#pragma unroll
                for (int r = 0; r < 2; r++) sum[h][r] += __shfl_xor_sync(~0u, sum[h][r], o);
        TSTAMP1T(5, 64);
        const uint32_t selA = odd ? 0x1044u : 0x4410u, selB = odd ? 0x3244u : 0x4432u, selH = hi ? selB : 0x4444u, selL = hi ? 0x4444u : selB;
        const uint32_t orow = sbase + A1_SM_O + (16 * warp + (lane & 15)) * 160 + (lane >> 4) * 16;
        uint32_t ob[10][2];
#pragma unroll
        for (int P = 0; P < 2; P++) {
            float os[2][4];
#pragma unroll
            for (int e = 0; e < 2; e++) {
                const int h = 2 * P + e;
                const float i0 = rcp_apx(sum[h][0]), i1 = rcp_apx(sum[h][1]);
                const uint32_t w0 = pack2(p[h][0] * i0, p[h][1] * i0), w1 = pack2(p[h][2] * i1, p[h][3] * i1);
                const uint32_t a00 = __byte_perm(w0, 0, selH), a02 = __byte_perm(w0, 0, selA), a03 = __byte_perm(w1, 0, selH);
                const uint32_t a10 = __byte_perm(w0, 0, selL), a11 = __byte_perm(w1, 0, selA), a13 = __byte_perm(w1, 0, selL);
#pragma unroll
                for (int dt = 0; dt < 3; dt++) {
                    const int j = 5 * P + (dt < 2 ? 3 * e + dt : 2);
                    float o[4] = {0.f, 0.f, 0.f, 0.f};
                    mma_bf16(o, a00, 0u, a02, a03, vb[j][0], vb[j][1]);
                    mma_bf16(o, a10, a11, 0u, a13, vb[j][2], vb[j][3]);
                    if (dt < 2) { ob[j][0] = pack2(o[0], o[1]); ob[j][1] = pack2(o[2], o[3]); }
                    else { os[e][0] = o[0]; os[e][1] = o[1]; os[e][2] = o[2]; os[e][3] = o[3]; }
                }
            }
            ob[5 * P + 2][0] = t < 2 ? pack2(os[0][0], os[0][1]) : pack2(os[1][0], os[1][1]);
            ob[5 * P + 2][1] = t < 2 ? pack2(os[0][2], os[0][3]) : pack2(os[1][2], os[1][3]);
        }
#pragma unroll
        for (int j = 0; j < 10; j += 2) stsm_x4(orow + 16 * j, ob[j][0], ob[j][1], ob[j + 1][0], ob[j + 1][1]);
        fence_async_smem();
        __syncwarp();
        if (on) {
            if (lane == 0) tma_store_2d(&tmOst, hg * 80, mb * 128 + 16 * warp, sbase + A1_SM_O + 16 * warp * 160);
            TSTAMP1T(4, 64);
            TSTAMP1(1);
            GSTAMP(g_tim1, 14);
            SPAN(1 + 4 * layer, 3);
            return;
        }
    }
    mbar_wait(bars + 144, 0);
    mbar_wait(bars + 8 * (A1_NST + 3), 1);
    const uint4* hin = g_halo + ((layer * 16 + mb - 1) * 8 + hg) * 320 + tid - 256;
    uint32_t hv[3][4] = {};
    if (mb > 0) {
#pragma unroll 1
        for (int it = 0; it < SPIN_MAX; it++) {
            bool ok = true;
#pragma unroll
            for (int k = 0; k < 3; k++)
                if (k < 2 || w < 10)
                    asm volatile("ld.relaxed.gpu.global.v4.u32 {%0,%1,%2,%3}, [%4];" : "=r"(hv[k][0]), "=r"(hv[k][1]), "=r"(hv[k][2]), "=r"(hv[k][3]) : "l"(hin + 128 * k) : "memory");
#pragma unroll
            for (int k = 0; k < 3; k++) ok = ok && hv[k][0] != ~0u && hv[k][1] != ~0u && hv[k][2] != ~0u && hv[k][3] != ~0u;
            if (ok) break;
        }
    }
    __syncwarp();
    TSTAMP1T(11, 256);
    const uint32_t hd = sbase + A1_SM_KV + (tid & 15) * A1_KVP + ((tid >> 4) & 1) * 16 + (w - 8) * 32;
#pragma unroll
    for (int k = 0; k < 3; k++)
        if (k < 2 || w < 10) stsm_x4(hd + 128 * k, hv[k][0], hv[k][1], hv[k][2], hv[k][3]);
    __syncwarp();
    if ((tid & 31) == 0) mbar_arrive(bar_kv);
}

constexpr int A2_THREADS = 288;
constexpr int A2_NA = 6;
#define A2_WPRE 4
#define A2_WLEAD 2
#define A2_RPOS 7
constexpr int A2_SM_A = 10 * WO_STAGE;
constexpr int A2_SM_R = A2_SM_A + A2_NA * 16384;
constexpr int A2_SM_BAR = A2_SM_R + 20480;
constexpr int A2_SMEM = A2_SM_BAR + 256 + 1024;

__global__ void __launch_bounds__(A2_THREADS, 1) a2_kernel(const int layer, const unsigned char* __restrict__ wo, const unsigned short* __restrict__ piv, float2* __restrict__ sum,
                                                           const __grid_constant__ CUtensorMap tmO, const __grid_constant__ CUtensorMap tmR,
                                                           const __grid_constant__ CUtensorMap tmX1) {
    extern __shared__ unsigned char smraw[];
    const uint32_t sbase = (smem_u32(smraw) + 1023) & ~1023u;
    const uint32_t bars = sbase + A2_SM_BAR, bar_e = bars + 80, bar_r = bars + 128;
    const int tid = threadIdx.x, w = __shfl_sync(~0u, tid >> 5, 0), wg = w >> 2;
    const int tile = sm_tile();
    if (tile >= 128) { sm_idle(2 * layer + 1); return; }
    const int mb = tile >> 3, cg = tile & 7;
    if (wg == 2) {
        const unsigned char* wsrc = wo + cg * 10 * WO_STAGE;
        if (tid == 256) {
            prefetch_tmap(&tmO);
#pragma unroll
            for (int i = 0; i < 17; i++) mbar_init(bars + 8 * i, i >= 10 && i < 16 ? 2 : 1);
            asm volatile("fence.mbarrier_init.release.cluster;" ::: "memory");
#pragma unroll
            for (int kb = 0; kb < A2_WPRE; kb += 2) {
                mbar_expect_tx(bars + 8 * kb, 16384 + 2 * WO_STAGE);
                bulk_load(sbase + kb * WO_STAGE, wsrc + kb * WO_STAGE, 2 * WO_STAGE, bars + 8 * kb);
            }
        }
        __syncwarp();
        asm volatile("bar.arrive 0, 288;" ::: "memory");
        if (tid == 256) {
#pragma unroll
            for (int kb = 0; kb < 10; kb++) if ((kb & 1) || kb >= A2_WPRE) mbar_expect_tx(bars + 8 * kb, (kb & 1) ? 16384 : 16384 + 2 * WO_STAGE);
            mbar_expect_tx(bar_r, 20480);
            pdl_sync();
#pragma unroll 1
            for (int kb = 0; kb < 10; kb++) {
                if (kb >= A2_NA) mbar_wait(bar_e + 8 * (kb - A2_NA), 0);
                tma_load_2d(sbase + A2_SM_A + (kb < A2_NA ? kb : kb - A2_NA) * 16384, &tmO, kb * 64, mb * 128, bars + 8 * kb);
                const int kw = kb + A2_WLEAD;
                if (!(kw & 1) && kw >= A2_WPRE && kw < 10) bulk_load(sbase + kw * WO_STAGE, wsrc + kw * WO_STAGE, 2 * WO_STAGE, bars + 8 * kw);
                if (kb == A2_RPOS) {
                    if (layer == 0) tma_load_2d(sbase + A2_SM_R, &tmR, cg * 80, mb * 128, bar_r);
                    else { tma_load_2d(sbase + A2_SM_R, &tmR, mb * 128, cg * 80, bar_r); tma_load_2d(sbase + A2_SM_R + 10240, &tmR, mb * 128 + 64, cg * 80, bar_r); }
                }
            }
        }
    } else {
        if (tid == 224) { prefetch_tmap(&tmR); prefetch_tmap(&tmX1); sm_started(2 * layer + 1); }
        asm volatile("bar.sync 0, 288;" ::: "memory");
        SPAN(2 + 4 * layer, 0);
        pdl_sync();
        SPAN(2 + 4 * layer, 1);
        TSTAMP2(0);
        TSTAMP4(0);
        if (threadIdx.x == 0) { GSTAMP(g_tim2, 15); }
        const int lane = tid & 31, warp = w, g = lane >> 2, t = lane & 3;
        const int row = layer * SEQ + mb * 128 + 16 * warp + g;
        const unsigned short pv0 = __ldcg(piv + row), pv1 = __ldcg(piv + row + 8);
        float acc[40];
        const uint64_t da0 = make_desc(sbase + A2_SM_A + wg * 8192, 16, 1024, 1), db0 = make_desc(sbase, 16, 1024, 1);
#pragma unroll 1
        for (int kb = 0; kb < 10; kb++) {
            if (kb == 0) TSTAMP4(11);
            mbar_wait(bars + 8 * kb, 0);
            TSTAMP4(1 + kb);
            wgmma_fence();
#pragma unroll
            for (int kk = 0; kk < 4; kk++) wgmma_n80<0, 0>(acc, da0 + (uint32_t)((kb < A2_NA ? kb : kb - A2_NA) * 1024 + kk * 2), db0 + (uint32_t)(kb * (WO_STAGE / 16) + kk * 2), kk ? 1 : kb);
            wgmma_commit();
            wgmma_wait<1>();
            if (kb > 0 && kb <= A2_NA && (tid & 127) == 0) mbar_arrive(bar_e + 8 * (kb - 1));
        }
        const uint32_t trow = ((lane & 7) + 8 * (lane >> 4)) * 128 + (((2 * (warp & 3) + ((lane >> 3) & 1)) ^ (lane & 7)) << 4);
        uint32_t xr[10][2];
        mbar_wait(bar_r, 0);
        if (layer == 0) {
#pragma unroll
            for (int j = 0; j < 10; j += 2) ldsm_x4(&xr[j][0], sbase + A2_SM_R + (16 * warp + (lane & 15)) * 160 + (lane >> 4) * 16 + 16 * j);
        } else {
#pragma unroll
            for (int j = 0; j < 10; j += 2) ldsm_x4_t(&xr[j][0], sbase + A2_SM_R + wg * 10240 + trow + 1024 * j);
        }
        mbar_wait(bar_e + 8 * (4 + wg), 0);
        wgmma_wait<0>();
        TSTAMP2(1);
        const float p0 = __uint_as_float((uint32_t)pv0 << 16), p1 = __uint_as_float((uint32_t)pv1 << 16);
        float s[4] = {0.f, 0.f, 0.f, 0.f};
#pragma unroll
        for (int j = 0; j < 10; j++) {
#pragma unroll
            for (int hh = 0; hh < 2; hh++) {
                const uint32_t a = pack2(acc[4 * j + 2 * hh], acc[4 * j + 2 * hh + 1]);
                const __nv_bfloat162 r = __hadd2_rn(*reinterpret_cast<const __nv_bfloat162*>(&xr[j][hh]), *reinterpret_cast<const __nv_bfloat162*>(&a));
                const uint32_t w = *reinterpret_cast<const uint32_t*>(&r);
                xr[j][hh] = w;
                const float d0 = __uint_as_float(w << 16) - (hh ? p1 : p0), d1 = __uint_as_float(w & 0xffff0000u) - (hh ? p1 : p0);
                s[2 * hh] += d0 + d1;
                s[2 * hh + 1] = fmaf(d0, d0, fmaf(d1, d1, s[2 * hh + 1]));
            }
        }
        const uint32_t so = sbase + A2_SM_A + (4 + wg) * 16384;
#pragma unroll
        for (int j = 0; j < 10; j += 2) stsm_x4_t(so + trow + 1024 * j, xr[j][0], xr[j][1], xr[j + 1][0], xr[j + 1][1]);
        fence_async_smem();
        TSTAMP2(2);
#pragma unroll
        for (int o = 1; o <= 2; o <<= 1)
#pragma unroll
            for (int i = 0; i < 4; i++) s[i] += __shfl_xor_sync(~0u, s[i], o);
        if (t < 2) asm volatile("red.relaxed.gpu.global.add.v2.f32 [%0], {%1, %2};" ::"l"(sum + layer * SEQ + (g >> 1) * 512 + (mb * 16 + 2 * warp + t) * 2 + (g & 1)), "f"(t ? s[2] : s[0]), "f"(t ? s[3] : s[1]) : "memory");
        if (wg) asm volatile("bar.sync 2, 128;" ::: "memory"); else asm volatile("bar.sync 1, 128;" ::: "memory");
        TSTAMP2(3);
        if ((tid & 127) == 0) tma_store_2d(&tmX1, mb * 128 + 64 * wg, cg * 80, so);
        TSTAMP2(4);
        GSTAMP(g_tim2, 14);
        SPAN(2 + 4 * layer, 3);
    }
}

static int h_nsm;
static void* h_sym[7];
static CUtensorMap h_tmX0, h_tmX1, h_tmOst, h_tmO, h_tmR0, h_tmR1, h_tmX1st, h_tmOut, h_tmWq, h_tmWo;
typedef CUresult (*PFN_encodeTiled)(CUtensorMap*, CUtensorMapDataType, cuuint32_t, void*, const cuuint64_t*, const cuuint64_t*,
                                    const cuuint32_t*, const cuuint32_t*, CUtensorMapInterleave, CUtensorMapSwizzle,
                                    CUtensorMapL2promotion, CUtensorMapFloatOOBfill);
static void make_tmap(CUtensorMap* tm, const void* ptr, uint64_t cols, uint64_t rows, uint32_t bc, uint32_t br, CUtensorMapSwizzle sw, uint64_t pitch = 0, uint64_t hi = 0) {
    static PFN_encodeTiled fn = nullptr;
    if (!fn) {
        void* p = nullptr; cudaDriverEntryPointQueryResult qr;
        cudaGetDriverEntryPoint("cuTensorMapEncodeTiled", &p, cudaEnableDefault, &qr);
        fn = (PFN_encodeTiled)p;
    }
    if (br == 0) {
        cuuint64_t dims[4] = {cols, 2, rows / 8, 4}; cuuint64_t strides[3] = {cols * 2, cols * 16, cols * 4};
        cuuint32_t box[4] = {bc, 2, 8, 4}; cuuint32_t es[4] = {1, 1, 1, 1};
        fn(tm, CU_TENSOR_MAP_DATA_TYPE_BFLOAT16, 4, const_cast<void*>(ptr), dims, strides, box, es, CU_TENSOR_MAP_INTERLEAVE_NONE, sw,
           CU_TENSOR_MAP_L2_PROMOTION_L2_128B, CU_TENSOR_MAP_FLOAT_OOB_FILL_NONE);
        return;
    }
    if (hi) {
        cuuint64_t dims[3] = {cols, rows, 32}; cuuint64_t strides[2] = {pitch * 2, hi * 2};
        cuuint32_t box[3] = {bc, br, 2}; cuuint32_t es[3] = {1, 1, 1};
        fn(tm, CU_TENSOR_MAP_DATA_TYPE_BFLOAT16, 3, const_cast<void*>(ptr), dims, strides, box, es, CU_TENSOR_MAP_INTERLEAVE_NONE, sw,
           CU_TENSOR_MAP_L2_PROMOTION_L2_128B, CU_TENSOR_MAP_FLOAT_OOB_FILL_NONE);
        return;
    }
    cuuint64_t dims[2] = {cols, rows}; cuuint64_t strides[1] = {(pitch ? pitch : cols) * 2};
    cuuint32_t box[2] = {bc, br}; cuuint32_t es[2] = {1, 1};
    fn(tm, CU_TENSOR_MAP_DATA_TYPE_BFLOAT16, 2, const_cast<void*>(ptr), dims, strides, box, es, CU_TENSOR_MAP_INTERLEAVE_NONE, sw,
       CU_TENSOR_MAP_L2_PROMOTION_L2_128B, CU_TENSOR_MAP_FLOAT_OOB_FILL_NONE);
}
template <typename... Args>
static void launch_pdl(void (*kern)(Args...), int grid, int block, int smem, Args... args) {
    cudaLaunchConfig_t cfg = {};
    cfg.gridDim = dim3(grid); cfg.blockDim = dim3(block); cfg.dynamicSmemBytes = smem; cfg.stream = cudaStreamPerThread;
    cudaLaunchAttribute at[1];
    at[0].id = cudaLaunchAttributeProgrammaticStreamSerialization; at[0].val.programmaticStreamSerializationAllowed = 1;
    cfg.attrs = at; cfg.numAttrs = 1;
    cudaLaunchKernelEx(&cfg, kern, args...);
}
static void launch_stage(int k, void* const* d_in, void* d_out) {
    const KgIn kg = {(const bf16*)d_in[4], (const bf16*)d_in[5], (const bf16*)d_in[6], (const bf16*)d_in[7], (const bf16*)d_in[8], (const bf16*)d_in[0], (const bf16*)d_in[1], (const bf16*)d_in[2],
                      (uint4*)h_sym[0], (uint4*)h_sym[1], (uint4*)h_sym[2], (uint4*)h_sym[3], (uint4*)h_sym[4], (float*)h_sym[5]};
    switch (k) {
        case 0: kgen_kernel<<<DM, KG_THREADS, 0, cudaStreamPerThread>>>(kg, h_tmWq, h_tmWo); break;
        case 1: launch_pdl(a1_kernel, h_nsm, A1_THREADS, A1_SMEM, 0, (const bf16*)d_in[0], (const unsigned char*)h_sym[1], h_tmX0, h_tmOst); break;
        case 2: launch_pdl(a2_kernel, h_nsm, A2_THREADS, A2_SMEM, 0, (const unsigned char*)h_sym[2], (const unsigned short*)h_sym[6], (float2*)h_sym[4], h_tmO, h_tmR0, h_tmX1st); break;
        case 3: launch_pdl(conv_kernel, DM / CV_CPB, CV_THREADS, CV_SMEM, (const bf16*)d_in[9], 0, h_tmOut); break;
        case 5: launch_pdl(a1_kernel, h_nsm, A1_THREADS, A1_SMEM, 1, (const bf16*)d_in[0], (const unsigned char*)h_sym[1], h_tmX1, h_tmOst); break;
        case 6: launch_pdl(a2_kernel, h_nsm, A2_THREADS, A2_SMEM, 1, (const unsigned char*)h_sym[2], (const unsigned short*)h_sym[6], (float2*)h_sym[4], h_tmO, h_tmR1, h_tmX1st); break;
        case 7: launch_pdl(conv_kernel, DM / CV_CPB, CV_THREADS, CV_SMEM, (const bf16*)d_in[9], 1, h_tmOut); break;
        default: break;
    }
}
static int n_stage_kernels() { return 9; }
static const char* stage_name(int k) { const char* n[] = {"kgen", "a1", "a2", "conv", "tr", "a1", "a2", "conv", "tr"}; return n[k]; }

extern "C" void kernel_launch(void* const* d_in, const int* in_sizes, int n_in, void* d_out, int out_size) {
    (void)in_sizes; (void)n_in; (void)out_size;
    static const void *p_in = nullptr, *p_w1 = nullptr, *p_w2 = nullptr, *p_out = nullptr;
    if (p_in != d_in[0] || p_w1 != d_in[1] || p_w2 != d_in[2] || p_out != d_out) {
        cudaFuncSetAttribute(conv_kernel, cudaFuncAttributeMaxDynamicSharedMemorySize, CV_SMEM);
        cudaFuncSetAttribute(kgen_kernel, cudaFuncAttributePreferredSharedMemoryCarveout, 100);
        cudaFuncSetAttribute(a1_kernel, cudaFuncAttributeMaxDynamicSharedMemorySize, A1_SMEM);
        cudaFuncSetAttribute(a2_kernel, cudaFuncAttributeMaxDynamicSharedMemorySize, A2_SMEM);
        int dev; cudaGetDevice(&dev); cudaDeviceGetAttribute(&h_nsm, cudaDevAttrMultiProcessorCount, dev);
        if (h_nsm != 132) h_nsm = 128;
        cudaGetSymbolAddress(&h_sym[0], g_tap); cudaGetSymbolAddress(&h_sym[1], g_wq); cudaGetSymbolAddress(&h_sym[2], g_wo);
        cudaGetSymbolAddress(&h_sym[3], g_halo); cudaGetSymbolAddress(&h_sym[4], g_sum); cudaGetSymbolAddress(&h_sym[5], g_csp); cudaGetSymbolAddress(&h_sym[6], g_piv);
        void *po, *px1, *px2;
        cudaGetSymbolAddress(&po, g_o); cudaGetSymbolAddress(&px1, g_x1T); cudaGetSymbolAddress(&px2, g_xcT);
        make_tmap(&h_tmO, po, 640, 2048, 64, 128, CU_TENSOR_MAP_SWIZZLE_128B);
        make_tmap(&h_tmOst, po, 640, 2048, 80, 16, CU_TENSOR_MAP_SWIZZLE_NONE);
        make_tmap(&h_tmX0, d_in[0], 640, 64, 64, 64, CU_TENSOR_MAP_SWIZZLE_128B, 640, 64 * 640);
        make_tmap(&h_tmX1, px2, 64, 640, 64, 64, CU_TENSOR_MAP_SWIZZLE_128B, XCP, 64);
        make_tmap(&h_tmR0, d_in[0], 640, 2048, 80, 128, CU_TENSOR_MAP_SWIZZLE_NONE);
        make_tmap(&h_tmR1, px2, 2048, 640, 64, 80, CU_TENSOR_MAP_SWIZZLE_128B, XCP);
        make_tmap(&h_tmX1st, px1, 2048, 640, 64, 80, CU_TENSOR_MAP_SWIZZLE_128B, XCP);
        make_tmap(&h_tmWq, d_in[1], 1920, 640, 32, 0, CU_TENSOR_MAP_SWIZZLE_64B);
        make_tmap(&h_tmWo, d_in[2], 640, 640, 32, 0, CU_TENSOR_MAP_SWIZZLE_64B);
        make_tmap(&h_tmOut, d_out, 640, 2048, 80, 8, CU_TENSOR_MAP_SWIZZLE_NONE);
        p_in = d_in[0]; p_w1 = d_in[1]; p_w2 = d_in[2]; p_out = d_out;
    }
    for (int k = 0; k < n_stage_kernels(); k++) launch_stage(k, d_in, d_out);
}
```

```cpp
#include <cuda_runtime.h>
#include <cuda_bf16.h>
#include <stdint.h>
#include <cuda.h>

typedef __nv_bfloat16 bf16;

constexpr int SEQ = 2048;
constexpr int DM = 640;
constexpr int NMODE = 192;

__device__ __forceinline__ float bf2f(bf16 v) { return __bfloat162float(v); }
__device__ __forceinline__ float rbf(float v) {
    uint32_t r;
    asm("cvt.rn.bf16x2.f32 %0, %1, %2;" : "=r"(r) : "f"(v), "f"(0.f));
    return __uint_as_float(r);
}
__device__ __forceinline__ uint32_t pack2(float lo, float hi) {
    __nv_bfloat162 t = __floats2bfloat162_rn(lo, hi);
    return *reinterpret_cast<uint32_t*>(&t);
}
__device__ __forceinline__ void pdl_sync() {
    asm volatile("griddepcontrol.wait;" ::: "memory");
    asm volatile("griddepcontrol.launch_dependents;" ::: "memory");
}
__device__ __forceinline__ float sqrt_apx(float v) { float r; asm("sqrt.approx.ftz.f32 %0, %1;" : "=f"(r) : "f"(v)); return r; }
__device__ __forceinline__ float rcp_apx(float v) { float r; asm("rcp.approx.ftz.f32 %0, %1;" : "=f"(r) : "f"(v)); return r; }
__device__ __forceinline__ uint32_t smem_u32(const void* p) { return (uint32_t)__cvta_generic_to_shared(p); }

constexpr int TPAD = 16;
constexpr int DLEN = 544;
constexpr int TAP_W2 = DLEN * 8, TAP_W3 = TAP_W2 + 768, TAP_C = TAP_W3 + 768, TAPB = TAP_C + 384;
__device__ __align__(128) uint4 g_tap[DM * 128];
#define XPAD 64
constexpr int XCP = SEQ + XPAD;
__device__ __align__(128) bf16 g_x1T[DM * XCP];
__device__ __align__(128) bf16 g_xcT[DM * XCP];
__device__ __align__(128) uint4 g_of[128 * 1280];
constexpr int WQ_STAGE = 240 * 128, WOB = 80 * 160;
__device__ __align__(128) uint4 g_wq[8 * 10 * WQ_STAGE / 16];
__device__ __align__(128) uint4 g_wo[64 * WOB / 16];
__device__ __align__(16) float g_csp[10 * 1920];
#define FSTR 32
__device__ __align__(128) float2 g_sum[2 * SEQ + 256 * FSTR];
__device__ __align__(16) bf16 g_piv[2 * SEQ];
__device__ __align__(128) bf16 g_yT[DM * XCP];
__device__ uint32_t g_epoch;
__device__ __align__(16) unsigned long long g_rstat[SEQ];
__device__ __align__(128) uint4 g_halo[640 * 148];
__device__ __forceinline__ unsigned long long tagw(uint32_t payload, uint32_t tag) { return ((unsigned long long)tag << 32) | payload; }
__device__ __forceinline__ ulonglong2 ld_tag2(const ulonglong2* p) {
    ulonglong2 v;
    asm volatile("ld.relaxed.gpu.global.v2.u64 {%0, %1}, [%2];" : "=l"(v.x), "=l"(v.y) : "l"(p) : "memory");
    return v;
}
__device__ __forceinline__ bool tag_ok(ulonglong2 v, uint32_t tag) { return (uint32_t)(v.x >> 32) == tag && (uint32_t)(v.y >> 32) == tag; }
__device__ __forceinline__ uint32_t ld_epoch() { uint32_t v; asm volatile("ld.relaxed.gpu.global.u32 %0, [%1];" : "=r"(v) : "l"(&g_epoch) : "memory"); return v + 1; }
constexpr int SPIN_MAX = 1 << 20;
__device__ uint32_t g_started[4];
__device__ __forceinline__ void sm_started(int slot) { asm volatile("red.relaxed.gpu.global.add.u32 [%0], 1;" ::"l"(g_started + slot) : "memory"); }
__device__ __noinline__ void sm_idle(int slot) {
    if (threadIdx.x) return;
    sm_started(slot);
    const uint32_t want = ld_epoch() * gridDim.x;
    pdl_sync();
#pragma unroll 1
    for (int it = 0; it < SPIN_MAX; it++) {
        uint32_t v;
        asm volatile("ld.relaxed.gpu.global.u32 %0, [%1];" : "=r"(v) : "l"(g_started + slot) : "memory");
        if ((int)(v - want) >= 0) break;
        __nanosleep(100);
    }
}
struct TileTab { uint32_t ns, pad; struct { unsigned char mb, hg, kb0, tile; uint32_t woff; } __align__(8) e[264]; };
__device__ __forceinline__ bool elect() {
    uint32_t p;
    asm volatile("{\n.reg .pred p;\nelect.sync _|p, 0xffffffff;\nselp.b32 %0, 1, 0, p;\n}" : "=r"(p));
    return p;
}
#define DBG_SYMS
#define TSTAMP(i)
#define TSTAMP1(i)
#define TSTAMP1T(i, t)
#define TSTAMP1X(i, t)
#define SPAN(k, i)
#define GSTAMP(arr, i)
#define TSTAMP2(i)
#define TSTAMP3(i)
#define TSTAMP4(i)
#define TSTAMPK(i, t)
#define DBGC(i)
#define DBGV(i, v)
#define DBGCAL(i)

__device__ __forceinline__ void mma_bf16(float* d, uint32_t a0, uint32_t a1, uint32_t a2, uint32_t a3, uint32_t b0, uint32_t b1) {
    asm volatile("mma.sync.aligned.m16n8k16.row.col.f32.bf16.bf16.f32 {%0,%1,%2,%3}, {%4,%5,%6,%7}, {%8,%9}, {%0,%1,%2,%3};"
                 : "+f"(d[0]), "+f"(d[1]), "+f"(d[2]), "+f"(d[3]) : "r"(a0), "r"(a1), "r"(a2), "r"(a3), "r"(b0), "r"(b1));
}
__device__ __forceinline__ void mma_bf16_k8(float* d, uint32_t a0, uint32_t a1, uint32_t b0) {
    asm volatile("mma.sync.aligned.m16n8k8.row.col.f32.bf16.bf16.f32 {%0,%1,%2,%3}, {%4,%5}, {%6}, {%0,%1,%2,%3};"
                 : "+f"(d[0]), "+f"(d[1]), "+f"(d[2]), "+f"(d[3]) : "r"(a0), "r"(a1), "r"(b0));
}
__device__ __forceinline__ void ldsm_x4(uint32_t* r, uint32_t addr) {
    asm volatile("ldmatrix.sync.aligned.m8n8.x4.shared.b16 {%0,%1,%2,%3}, [%4];"
                 : "=r"(r[0]), "=r"(r[1]), "=r"(r[2]), "=r"(r[3]) : "r"(addr));
}

__device__ __forceinline__ void ldsm_x4_t(uint32_t* r, uint32_t addr) {
    asm volatile("ldmatrix.sync.aligned.m8n8.x4.trans.shared.b16 {%0,%1,%2,%3}, [%4];"
                 : "=r"(r[0]), "=r"(r[1]), "=r"(r[2]), "=r"(r[3]) : "r"(addr));
}
__device__ __forceinline__ void mbar_init(uint32_t bar, int count) { asm volatile("mbarrier.init.shared::cta.b64 [%0], %1;" ::"r"(bar), "r"(count)); }
__device__ __forceinline__ void mbar_arrive(uint32_t bar) { asm volatile("mbarrier.arrive.shared::cta.b64 _, [%0];" ::"r"(bar) : "memory"); }
__device__ __forceinline__ void mbar_wait(uint32_t bar, uint32_t parity) {
    asm volatile("{\n.reg .pred p;\nWAIT_LOOP:\n"
                 "mbarrier.try_wait.parity.shared::cta.b64 p, [%0], %1;\n"
                 "@p bra.uni WAIT_DONE;\nbra.uni WAIT_LOOP;\nWAIT_DONE:\n}" ::"r"(bar), "r"(parity) : "memory");
}

__device__ __forceinline__ void mbar_expect_tx(uint32_t bar, uint32_t bytes) {
    asm volatile("mbarrier.arrive.expect_tx.shared::cta.b64 _, [%0], %1;" ::"r"(bar), "r"(bytes) : "memory");
}
__device__ __forceinline__ void tma_load_2d(uint32_t dst, const void* tmap, int c0, int c1, uint32_t bar) {
    asm volatile("cp.async.bulk.tensor.2d.shared::cluster.global.mbarrier::complete_tx::bytes [%0], [%1, {%3, %4}], [%2];"
                 ::"r"(dst), "l"(tmap), "r"(bar), "r"(c0), "r"(c1) : "memory");
}
__device__ __forceinline__ void tma_load_3d(uint32_t dst, const void* tmap, int c0, int c1, int c2, uint32_t bar) {
    asm volatile("cp.async.bulk.tensor.3d.shared::cluster.global.mbarrier::complete_tx::bytes [%0], [%1, {%3, %4, %5}], [%2];"
                 ::"r"(dst), "l"(tmap), "r"(bar), "r"(c0), "r"(c1), "r"(c2) : "memory");
}
__device__ __forceinline__ void fence_async_smem() { asm volatile("fence.proxy.async.shared::cta;" ::: "memory"); }
__device__ __forceinline__ void bulk_load(uint32_t dst, const void* src, uint32_t bytes, uint32_t bar) {
    asm volatile("cp.async.bulk.shared::cluster.global.mbarrier::complete_tx::bytes [%0], [%1], %2, [%3];"
                 ::"r"(dst), "l"(src), "r"(bytes), "r"(bar) : "memory");
}
__device__ __forceinline__ void tma_store_2d(const void* tmap, int c0, int c1, uint32_t src) {
    asm volatile("cp.async.bulk.tensor.2d.global.shared::cta.bulk_group [%0, {%1, %2}], [%3];" ::"l"(tmap), "r"(c0), "r"(c1), "r"(src) : "memory");
    asm volatile("cp.async.bulk.commit_group;" ::: "memory");
    asm volatile("cp.async.bulk.wait_group.read 0;" ::: "memory");
}
__device__ __forceinline__ void stsm_x4(uint32_t addr, uint32_t r0, uint32_t r1, uint32_t r2, uint32_t r3) {
    asm volatile("stmatrix.sync.aligned.m8n8.x4.shared.b16 [%0], {%1,%2,%3,%4};" ::"r"(addr), "r"(r0), "r"(r1), "r"(r2), "r"(r3) : "memory");
}
__device__ __forceinline__ void stsm_x4_t(uint32_t addr, uint32_t r0, uint32_t r1, uint32_t r2, uint32_t r3) {
    asm volatile("stmatrix.sync.aligned.m8n8.x4.trans.shared.b16 [%0], {%1,%2,%3,%4};" ::"r"(addr), "r"(r0), "r"(r1), "r"(r2), "r"(r3) : "memory");
}
__device__ __forceinline__ void prefetch_tmap(const void* tmap) { asm volatile("prefetch.tensormap [%0];" ::"l"(tmap) : "memory"); }

__device__ __forceinline__ float2 cexp_at(float wr2, float wi, float p) {
    float er;
    asm("ex2.approx.ftz.f32 %0, %1;" : "=f"(er) : "f"(wr2 * p));
    float th = wi * p;
    const float k = rintf(th * 0.15915494309189535f);
    th = fmaf(k, -6.2831854820251465f, th);
    th = fmaf(k, 1.7484555314695172e-7f, th);
    return make_float2(er * __cosf(th), er * __sinf(th));
}
__device__ __forceinline__ float2 cmul(float2 a, float2 b) {
    return make_float2(fmaf(a.x, b.x, -a.y * b.y), fmaf(a.x, b.y, a.y * b.x));
}
__device__ __forceinline__ float2 csqr(float2 a) { return make_float2(fmaf(a.x, a.x, -a.y * a.y), (a.x + a.x) * a.y); }
__device__ __forceinline__ uint32_t packh(float2 v) {
    uint32_t r;
    asm("cvt.rn.f16x2.f32 %0, %1, %2;" : "=r"(r) : "f"(v.y), "f"(v.x));
    return r;
}
__device__ __forceinline__ void mma_f16(float* d, uint32_t a0, uint32_t a1, uint32_t a2, uint32_t a3, uint32_t b0, uint32_t b1) {
    asm volatile("mma.sync.aligned.m16n8k16.row.col.f32.f16.f16.f32 {%0,%1,%2,%3}, {%4,%5,%6,%7}, {%8,%9}, {%0,%1,%2,%3};"
                 : "+f"(d[0]), "+f"(d[1]), "+f"(d[2]), "+f"(d[3]) : "r"(a0), "r"(a1), "r"(a2), "r"(a3), "r"(b0), "r"(b1));
}

struct KgIn { const bf16 *logA, *Aim, *Cre, *Cim, *logdt, *x, *wqkv, *wo; uint4 *tap, *wq, *wop, *halo, *sum; float* csp; };
constexpr int KG_THREADS = NMODE / 2;

__global__ void __launch_bounds__(KG_THREADS, 5) kgen_kernel(const KgIn in, const __grid_constant__ CUtensorMap tmWq, const __grid_constant__ CUtensorMap tmWo) {
    __shared__ __align__(8) unsigned long long wbar[3];
    __shared__ __align__(1024) uint4 tab[3 * 896];
    const int d = blockIdx.x, tid = threadIdx.x, lane = tid & 31, warp = __shfl_sync(~0u, tid >> 5, 0);
    SPAN(0, 0); SPAN(0, 1);
    TSTAMPK(0, 0);
    asm volatile("griddepcontrol.launch_dependents;" ::: "memory");
    const bf16 pdt = in.logdt[d];
    const uint32_t pla = reinterpret_cast<const uint32_t*>(in.logA)[d * KG_THREADS + tid], pai = reinterpret_cast<const uint32_t*>(in.Aim)[d * KG_THREADS + tid];
    const uint32_t pcr = reinterpret_cast<const uint32_t*>(in.Cre)[d * KG_THREADS + tid], pci = reinterpret_cast<const uint32_t*>(in.Cim)[d * KG_THREADS + tid];
    const bf16* pfq = tid < 30 ? in.wqkv + (size_t)(d * 30 + tid) * 64 : tid < 40 ? in.wo + (size_t)(d * 10 + tid - 30) * 64 : in.x + (size_t)(d * 32 + tid - 40) * 64;
    if (tid < 72) asm volatile("prefetch.global.L2 [%0];" ::"l"(pfq));
    asm volatile("st.global.v4.u32 [%0], {%1,%1,%1,%1};" ::"l"(in.halo + d * 148 + tid), "r"(~0u));
    if (tid < 52) asm volatile("st.global.v4.u32 [%0], {%1,%1,%1,%1};" ::"l"(in.halo + d * 148 + 96 + tid), "r"(~0u));
    const uint32_t tw = smem_u32(tab) + warp * 14336;
    if (lane == 0) { mbar_init(smem_u32(wbar + warp), 1); prefetch_tmap(d >= 200 ? &tmWo : &tmWq); }
    const int g = lane >> 2, t = lane & 3;
    const uint32_t sta = tw + lane * 128 + ((2 * (lane & 3) + ((lane >> 2) & 1)) << 4);
    const uint32_t lda = tw + t * 128 + ((g ^ (2 * t)) << 4);
    const uint32_t stb = tw + 12288 + lane * 64 + ((4 * ((lane >> 1) & 1) + ((lane >> 2) & 3)) << 3);
    const uint32_t ldb = tw + 12288 + t * 64 + ((g ^ (4 * (t >> 1))) << 3);
    auto sts4 = [&](int e, int off, uint32_t a, uint32_t b, uint32_t c, uint32_t dd) {
        asm volatile("st.shared.v4.u32 [%0], {%1,%2,%3,%4};" ::"r"((sta ^ (e << 4)) + off), "r"(a), "r"(b), "r"(c), "r"(dd) : "memory");
    };
    auto lds4 = [&](int sp, int off, uint32_t* r) {
        asm volatile("ld.shared.v4.u32 {%0,%1,%2,%3}, [%4];" : "=r"(r[0]), "=r"(r[1]), "=r"(r[2]), "=r"(r[3]) : "r"((lda ^ ((sp & 1) << 4)) + sp * 512 + off) : "memory");
    };
    const float dt = rbf(expf(bf2f(pdt)));
    float2 C[2], y1[2], z8[2], y128[2];
    float cmax = 0.f;
#pragma unroll
    for (int m = 0; m < 2; m++) {
        const float wr2 = -rbf(expf(__uint_as_float(m ? pla & 0xffff0000u : pla << 16))) * dt * 1.4426950408889634f;
        const float wi = __uint_as_float(m ? pai & 0xffff0000u : pai << 16) * dt;
        C[m] = make_float2(__uint_as_float(m ? pcr & 0xffff0000u : pcr << 16) * dt, -__uint_as_float(m ? pci & 0xffff0000u : pci << 16) * dt);
        cmax = fmaxf(cmax, fmaxf(fabsf(C[m].x), fabsf(C[m].y)));
        y1[m] = cexp_at(wr2, -wi, 1.f); z8[m] = cexp_at(wr2, wi, 8.f); y128[m] = cexp_at(wr2, -wi, 128.f);
    }
    const int ex = min(max((int)(__reduce_max_sync(~0u, __float_as_uint(cmax)) >> 23), 20), 240);
    const float scale = __uint_as_float((uint32_t)(127 + 10 + 127 - ex) << 23), unscale = 2.0f * __uint_as_float((uint32_t)(ex - 10) << 23);
    TSTAMPK(4, 0);
    float k2048 = 0.f;
    float acc[5][4];
#pragma unroll
    for (int j = 0; j < 5; j++)
#pragma unroll
        for (int k = 0; k < 4; k++) acc[j][k] = 0.f;
    uint32_t af[8][4];
    {
        float2 h0[2], h1[2], g0[2], g1[2], g2[2], g2b[2], g3[2], g4[2], y2[2], y4[2];
#pragma unroll
        for (int m = 0; m < 2; m++) {
            h0[m] = make_float2(1.f, 0.f); h1[m] = csqr(csqr(csqr(z8[m])));
            g0[m] = make_float2(C[m].x * scale, C[m].y * scale);
            g1[m] = cmul(g0[m], y128[m]);
            const float2 y256 = csqr(y128[m]), y512 = csqr(y256);
            g2b[m] = g2[m] = cmul(g0[m], y256); g3[m] = cmul(g0[m], y512); g4[m] = cmul(g3[m], y512);
            y2[m] = csqr(y1[m]); y4[m] = csqr(y2[m]);
            const float2 y1024 = csqr(y512);
            k2048 += fmaf(g4[m].x, y1024.x, -g4[m].y * y1024.y);
        }
#pragma unroll
        for (int e = 0; e < 8; e++) {
            sts4(e, 0, packh(h0[0]), packh(h1[0]), packh(h0[1]), packh(h1[1]));
            sts4(e, 4096, packh(g0[0]), packh(g0[1]), packh(g1[0]), packh(g1[1]));
#pragma unroll
            for (int m = 0; m < 2; m++)
                if (e < 7) { h0[m] = e ? cmul(h0[m], z8[m]) : z8[m]; h1[m] = cmul(h1[m], z8[m]); g0[m] = cmul(g0[m], y1[m]); g1[m] = cmul(g1[m], y1[m]); }
            if (e < 5) k2048 += __shfl_xor_sync(~0u, k2048, 1 << e);
        }
        __syncwarp();
#pragma unroll
        for (int e = 0; e < 8; e++) {
            uint32_t b[4];
            lds4(e, 0, af[e]); lds4(e, 4096, b);
            sts4(e, 8192, packh(g2[0]), packh(g2[1]), packh((e & 1) ? cmul(g3[0], y4[0]) : g3[0]), packh((e & 1) ? cmul(g3[1], y4[1]) : g3[1]));
            asm volatile("st.shared.v2.u32 [%0], {%1,%2};" ::"r"(stb ^ (e << 3)), "r"(packh(g4[0])), "r"(packh(g4[1])) : "memory");
#pragma unroll
            for (int m = 0; m < 2; m++)
                if (e < 7) {
                    g2[m] = e == 3 ? cmul(g2b[m], y128[m]) : cmul(g2[m], y2[m]);
                    if (e & 1) g3[m] = cmul(g3[m], y128[m]);
                    g4[m] = cmul(g4[m], y128[m]);
                }
            mma_f16(acc[0], af[e][0], af[e][1], af[e][2], af[e][3], b[0], b[1]);
            mma_f16(acc[1], af[e][0], af[e][1], af[e][2], af[e][3], b[2], b[3]);
        }
    }
    TSTAMPK(6, 0);
    const int job = d * 3 + warp;
    const bool isq = job < 600;
    const int scol = (isq ? job / 10 : (job - 600) >> 3) * 32, skb = isq ? job - (job / 10) * 10 : job & 7;
    fence_async_smem();
    __syncwarp();
    if (job < 760) {
        if (lane == 0) {
            mbar_expect_tx(smem_u32(wbar + warp), isq ? 4096 : 5120);
            if (isq) asm volatile("cp.async.bulk.tensor.4d.shared::cluster.global.mbarrier::complete_tx::bytes [%0], [%1, {%3, %4, %5, %4}], [%2];"
                                  ::"r"(tw + 4096), "l"(&tmWq), "r"(smem_u32(wbar + warp)), "r"(scol), "r"(0), "r"(skb * 8) : "memory");
            else tma_load_2d(tw + 3072, &tmWo, scol, skb * 80, smem_u32(wbar + warp));
        }
    } else if (job < 760 + 64) in.sum[(job - 760) * 32 + lane] = make_uint4(0, 0, 0, 0);
    else if (job < 760 + 80) reinterpret_cast<uint32_t*>(in.sum + 2048)[((job - 824) * 32 + lane) * FSTR] = 0;
#pragma unroll
    for (int sp = 0; sp < 8; sp++) {
        uint32_t c[4], e0, e1;
        lds4(sp, 8192, c);
        asm volatile("ld.shared.v2.u32 {%0,%1}, [%2];" : "=r"(e0), "=r"(e1) : "r"((ldb ^ ((sp & 3) << 3)) + sp * 256) : "memory");
        mma_f16(acc[2], af[sp][0], af[sp][1], af[sp][2], af[sp][3], c[0], c[1]);
        mma_f16(acc[3], af[sp][0], af[sp][1], af[sp][2], af[sp][3], c[2], c[3]);
        mma_f16(acc[4], af[sp][0], af[sp][1], af[sp][2], af[sp][3], e0, e1);
    }
    {
        float* Pp = reinterpret_cast<float*>(tab + warp * 896);
#pragma unroll
        for (int h = 0; h < 2; h++) {
            const int b = g + 8 * h;
            *reinterpret_cast<float2*>(Pp + 8 * b + 2 * t) = make_float2(acc[0][2 * h] * unscale, acc[0][2 * h + 1] * unscale);
            *reinterpret_cast<float2*>(Pp + 128 + 8 * b + 2 * t) = make_float2(acc[1][2 * h] * unscale, acc[1][2 * h + 1] * unscale);
            *reinterpret_cast<float2*>(Pp + 256 + 4 * b + 2 * (t & 1) + 64 * (t >> 1)) = make_float2(acc[2][2 * h] * unscale, acc[2][2 * h + 1] * unscale);
            *reinterpret_cast<float2*>(Pp + 384 + 2 * b + 32 * t) = make_float2(acc[3][2 * h] * unscale, acc[3][2 * h + 1] * unscale);
            Pp[512 + b + 32 * t] = acc[4][2 * h] * unscale;
            Pp[512 + b + 32 * t + 16] = acc[4][2 * h + 1] * unscale;
        }
        if (lane == 0) Pp[640] = k2048 * unscale;
    }
    TSTAMPK(7, 0);
    __syncthreads();
    TSTAMPK(9, 0);
    const float* Kp = reinterpret_cast<const float*>(tab);
    auto ksum = [&](int i) -> float { return (Kp[i] + Kp[3584 + i]) + Kp[7168 + i]; };
    auto ksum4 = [&](int q) -> float4 {
        const float4 a = reinterpret_cast<const float4*>(Kp)[q], b = reinterpret_cast<const float4*>(Kp)[896 + q], c = reinterpret_cast<const float4*>(Kp)[1792 + q];
        return make_float4((a.x + b.x) + c.x, (a.y + b.y) + c.y, (a.z + b.z) + c.z, (a.w + b.w) + c.w);
    };
    {
        uint2* E4 = reinterpret_cast<uint2*>(in.tap + d * 128);
        float4 v = ksum4(tid), u = ksum4(96 + min(tid, 64));
        const float cor = rbf(ksum(tid == 95 ? 384 : 512));
        if (tid == 95) v.w -= cor;
        if (tid == 31) u.w -= cor;
        const uint32_t lo = pack2(v.x, v.y), hi = pack2(v.z, v.w);
        if (tid < 64) {
            E4[6 + tid] = make_uint2(lo, hi);
            E4[(tid < 32 ? 159 : 209 - 32) + tid] = make_uint2(pack2(u.x, u.y), pack2(u.z, u.w));
        } else {
            const uint32_t nx = __shfl_down_sync(~0u, lo, 1);
            in.tap[d * 128 + 35 + tid - 64] = make_uint4(__byte_perm(lo, 0, 0x1010), __byte_perm(lo, hi, 0x5432), __byte_perm(hi, 0, 0x1010), __byte_perm(hi, tid == 95 ? 0u : nx, 0x5432));
            if (tid == 64) E4[241] = make_uint2(pack2(u.x, 0.f), 0u);
        }
    }
    TSTAMPK(10, 0);
    if (isq) {
        mbar_wait(smem_u32(wbar + warp), 0);
        const uint32_t src = tw + 4096 + ((lane >> 3) * 16 + (lane & 7)) * 64;
#pragma unroll
        for (int cg = 0; cg < 4; cg++) {
            const int col = scol + 8 * cg, sec = col / DM, r = col - sec * DM, hg = r / 80;
            const int n = hg * 160 + sec * 80 + r;
            unsigned char* dst = reinterpret_cast<unsigned char*>(in.wq) + (hg * 9 + (hg < 4 ? skb : skb < 5 ? skb + 5 : skb - 5)) * WQ_STAGE + (n + g) * 128;
            float cs[4] = {0.f, 0.f, 0.f, 0.f};
#pragma unroll
            for (int h = 0; h < 2; h++) {
                uint32_t w[4];
                ldsm_x4_t(w, src + h * 512 + ((cg ^ ((lane >> 1) & 3)) << 4));
                *reinterpret_cast<uint4*>(dst + (((4 * h + t) ^ g) << 4)) = make_uint4(w[0], w[1], w[2], w[3]);
                mma_bf16(cs, 0x3f803f80u, 0u, 0x3f803f80u, 0u, w[0], w[1]);
                mma_bf16(cs, 0x3f803f80u, 0u, 0x3f803f80u, 0u, w[2], w[3]);
            }
            if (g == cg) *reinterpret_cast<float2*>(in.csp + skb * 1920 + n + 2 * t) = make_float2(cs[0], cs[1]);
        }
    } else if (job < 760) {
        mbar_wait(smem_u32(wbar + warp), 0);
#pragma unroll 1
        for (int cg = 0; cg < 4; cg++) {
            const int col = scol + 8 * cg, hg = col / 80;
            unsigned char* dst = reinterpret_cast<unsigned char*>(in.wop) + (hg * 7 + (skb == hg ? 0 : skb + (skb < hg))) * WOB + col * 160 + g * 16;
            const int r0 = lane, r2 = 64 + (lane & 15);
            uint32_t w[12];
            ldsm_x4_t(w, tw + 3072 + r0 * 64 + ((cg ^ ((r0 >> 1) & 3)) << 4));
            ldsm_x4_t(w + 4, tw + 3072 + 2048 + r0 * 64 + ((cg ^ ((r0 >> 1) & 3)) << 4));
            ldsm_x4_t(w + 8, tw + 3072 + r2 * 64 + ((cg ^ ((r2 >> 1) & 3)) << 4));
            *reinterpret_cast<uint4*>(dst + t * 128) = make_uint4(w[0], w[1], w[2], w[3]);
            *reinterpret_cast<uint4*>(dst + 512 + t * 128) = make_uint4(w[4], w[5], w[6], w[7]);
            *reinterpret_cast<uint2*>(dst + 1024 + (t >> 1) * 128 + (t & 1) * 8) = make_uint2(w[8], w[9]);
        }
    }
    TSTAMPK(11, 0);
    SPAN(0, 3);
}

#define CV_MODE 0
#define CV_LD __ldcg
#define CV_LDX __ldcg
#define CV_SLEEP 100
constexpr int CV_CPB = 5;
constexpr int CV_THREADS = 512;
constexpr int UPADF = 128;
constexpr int ULEN = UPADF + SEQ + 80;
constexpr int XLEN = SEQ + 16;
constexpr int BX_5 = 0, BX_3 = 3264, BX_9 = 6528, BX_7 = 8960, BX_LEN = 11392;
constexpr int CV_SM_T = 0;
constexpr int CV_SM_B = CV_CPB * TAPB;
constexpr int CV_SM_U = CV_SM_B + CV_CPB * BX_LEN;
constexpr int CV_SM_X = CV_SM_U + CV_CPB * ULEN * 2;
constexpr int CV_SM_Y = CV_SM_X + CV_CPB * XLEN * 2;
constexpr int CV_SM_P = CV_SM_Y + CV_CPB * XLEN * 2;
constexpr int CV_SM_CNT = CV_SM_P + 6 * 4096;
constexpr int CV_SM_O = (CV_SM_CNT + 128 + 127) & ~127;
constexpr int CV_SMEM = CV_SM_O + 20480;
static_assert(CV_SM_B % 128 == 0 && CV_SM_CNT % 16 == 0, "layout");

__device__ __forceinline__ uint32_t sub2(uint32_t x, uint32_t m) {
    const __nv_bfloat162 d = __hsub2(*reinterpret_cast<const __nv_bfloat162*>(&x), *reinterpret_cast<const __nv_bfloat162*>(&m));
    return *reinterpret_cast<const uint32_t*>(&d);
}
__device__ __forceinline__ uint32_t add2(uint32_t x, uint32_t y) {
    const __nv_bfloat162 d = __hadd2_rn(*reinterpret_cast<const __nv_bfloat162*>(&x), *reinterpret_cast<const __nv_bfloat162*>(&y));
    return *reinterpret_cast<const uint32_t*>(&d);
}
__device__ __forceinline__ void cp_async16(uint32_t dst, const void* src) {
    asm volatile("cp.async.cg.shared.global [%0], [%1], 16;" ::"r"(dst), "l"(src));
}
__device__ __forceinline__ void cp_async_wait_all() { asm volatile("cp.async.wait_all;" ::: "memory"); }

template <bool FULL>
__device__ __forceinline__ void direct_pass(float (&acc)[8][4], uint32_t ub, uint32_t o0, uint32_t o1, const uint2* __restrict__ Tp, bool first_half) {
    uint32_t sw[8][8];
#pragma unroll
    for (int j = 0; j < 8; j++) { ldsm_x4(&sw[j][0], ub + o0 + j * 256); ldsm_x4(&sw[j][4], ub + o1 + j * 256); }
#pragma unroll
    for (int M = 0; M < 4; M++) {
#pragma unroll
        for (int i = 0; i < 4; i++) {
            const uint2 hi = Tp[128 * M + 16 * i], lo = Tp[128 * M + 16 * i - 8];
#pragma unroll
            for (int j = FULL ? 0 : M; j < 8; j++) mma_bf16(acc[j], hi.x, hi.y, lo.x, lo.y, sw[(j - M) & 7][2 * i], sw[(j - M) & 7][2 * i + 1]);
        }
        if (FULL) {
            ldsm_x4(&sw[7 - M][0], ub + o0 - (M + 1) * 256);
            if (M < 3) ldsm_x4(&sw[7 - M][4], ub + o1 - (M + 1) * 256);
        }
    }
    if (first_half) {
        const uint2 hi = Tp[512], lo = Tp[504];
#pragma unroll
        for (int j = FULL ? 0 : 4; j < 8; j++) mma_bf16(acc[j], hi.x, hi.y, lo.x, lo.y, sw[(j - 4) & 7][0], sw[(j - 4) & 7][1]);
    }
}
__device__ __forceinline__ uint32_t fin2(uint32_t y, uint32_t u, uint32_t dk) {
    typedef __nv_bfloat162 b2;
    const b2 r = __hadd2_rn(*reinterpret_cast<const b2*>(&y), __hmul2_rn(*reinterpret_cast<const b2*>(&u), *reinterpret_cast<const b2*>(&dk)));
    return *reinterpret_cast<const uint32_t*>(&r);
}
__global__ void __launch_bounds__(CV_THREADS, 1) conv_kernel(const bf16* __restrict__ Dskip, int layer, const uint4* __restrict__ piv, const float4* __restrict__ sum, const bf16* __restrict__ x1T,
                                                             bf16* __restrict__ dst, const uint4* __restrict__ tap, bf16* __restrict__ yT, const __grid_constant__ CUtensorMap tmOut) {
    extern __shared__ __align__(128) unsigned char sm[];
    SPAN(3 + 4 * layer, 0);
    bf16* Us = reinterpret_cast<bf16*>(sm + CV_SM_U);
    bf16* Xs = reinterpret_cast<bf16*>(sm + CV_SM_X);
    bf16* Ys = reinterpret_cast<bf16*>(sm + CV_SM_Y);
    const int tid = threadIdx.x, lane = tid & 31, warp = __shfl_sync(~0u, tid >> 5, 0);
    const int d0 = blockIdx.x * CV_CPB, tile = blockIdx.x; (void)tile;
    const int g = lane >> 2, ti = lane & 3;
    const int e = g - 2 * ti;
    uint32_t lds_off[4];
    uint32_t off2, off3, offc;
    {
        const int mat = lane >> 3, r = lane & 7;
#pragma unroll
        for (int pr = 0; pr < 4; pr++) {
            const int iw = 2 * pr + (mat >> 1), half = mat & 1;
            const int chunk = (UPADF - 16 * iw + 16 * r + 8 * half) >> 3;
            lds_off[pr] = (uint32_t)((chunk ^ ((chunk >> 3) & 1)) * 16);
        }
        const int j2 = 13 + r + 8 * (mat >> 1), j3 = j2 + 2, i0 = 8 * (mat & 1);
        off2 = (j2 & 1) ? BX_3 + (4 * j2 + i0 + 84) * 2 : BX_5 + (4 * j2 + i0 + 80) * 2;
        off3 = ((j3 & 1) ? BX_7 : BX_9) + (8 * j3 + i0 + 136) * 2;
        const int cc = (UPADF + 16 * (r + (mat >> 1)) + i0) >> 3;
        offc = (uint32_t)((cc ^ ((cc >> 3) & 1)) * 16);
    }
#define CV_WX 0
    const int wv = warp ^ CV_WX;
    const uint32_t rtab = wv < 8 ? (wv < 4 ? 0x0B090200u : 0x0C0A0301u) : (wv < 12 ? 0x13111008u : 0x1412241Cu);
    const int rl = (rtab >> (8 * (warp & 3))) & 0xff, type = rl >> 3, c = rl & 7;
    const int H = (type == 1 || type == 2) ? 1 : 0, T0 = 8 * H;
    uint32_t toff = CV_SM_T + c * TAPB + (TPAD + e) * 8;
    uint32_t ubase = smem_u32(Us + c * ULEN);
    const uint32_t bbase = smem_u32(sm + CV_SM_B + c * BX_LEN);
    uint32_t rd0, rd1;
    {
        const uint32_t rstart = wv < 8 ? (wv < 4 ? 0x02000000u : 0x06040000u) : (wv < 12 ? 0x0C0B0A08u : 0x1E1D150Fu);
        const uint32_t rcount = wv < 8 ? 0x02020000u : (wv < 12 ? 0x03010102u : 0x01010806u);
        rd0 = (rstart >> (8 * (warp & 3))) & 0xff; rd1 = rd0 + ((rcount >> (8 * (warp & 3))) & 0xff);
    }
    asm volatile("" : "+r"(lds_off[0]), "+r"(lds_off[1]), "+r"(lds_off[2]), "+r"(lds_off[3]), "+r"(ubase), "+r"(toff), "+r"(rd0), "+r"(rd1));
    const uint2* Tc = reinterpret_cast<const uint2*>(sm + toff);
    TSTAMP1X(9, 256);
    unsigned short dskr;
    asm volatile("ld.global.nc.u16 %0, [%1];" : "=h"(dskr) : "l"(Dskip + d0 + min(lane, CV_CPB - 1)));
    if (tid >= 256) {
        const int t2 = tid - 256;
        if (t2 == 0) {
            mbar_init(smem_u32(sm + CV_SM_CNT) + 104, 1);
            asm volatile("fence.mbarrier_init.release.cluster;" ::: "memory");
            mbar_expect_tx(smem_u32(sm + CV_SM_CNT) + 104, CV_CPB * 2048);
            bulk_load(smem_u32(sm + CV_SM_O), tap + d0 * 128, CV_CPB * 2048, smem_u32(sm + CV_SM_CNT) + 104);
        } else if (lane == 0) {
            mbar_init(smem_u32(sm + CV_SM_CNT) + 16 * (warp - 9), warp == 15 ? 16 : 1);
            if (warp < 15) mbar_init(smem_u32(sm + CV_SM_CNT) + 16 * (warp - 9) + 8, 1);
            else if (layer) prefetch_tmap(&tmOut);
        }
        if (t2 < 149) {
            const int k = t2;
            const int off = k < 18 ? BX_5 + 8 * k : k < 37 ? BX_3 + 8 * (k - 18) : k < 69 ? BX_9 + 8 * (k - 37) : k < 101 ? BX_7 + 8 * (k - 69)
                          : k < 133 ? 8 * (k - 101) : (UPADF + SEQ) * 2 + 8 * (k - 133);
#pragma unroll
            for (int c = 0; c < CV_CPB; c++) *reinterpret_cast<uint2*>(sm + (k < 101 ? CV_SM_B + c * BX_LEN : CV_SM_U + c * ULEN * 2) + off) = make_uint2(0, 0);
        }
        asm volatile("bar.sync 1, 256;" ::: "memory");
        TSTAMP1X(10, 256);
        mbar_wait(smem_u32(sm + CV_SM_CNT) + 104, 0);
        TSTAMP1X(11, 256);
#pragma unroll 1
        for (int r = t2; r < 392; r += 256) {
            const bool dd = r < 272, cc = r >= 368;
            const uint32_t* E2 = reinterpret_cast<const uint32_t*>(sm + CV_SM_O) + (dd ? r + 3 : r < 320 ? 301 + 2 * (r - 272) : cc ? 417 : 401 + 2 * (r - 320));
            const uint32_t* E3 = E2 + (dd ? 4 : cc ? 0 : 1);
            const uint32_t s0 = !cc ? 0x7610u : r == 382 ? 0x1044u : 0x4444u, s1 = !cc ? 0x7610u : r == 378 ? 0x1044u : 0x4444u;
            const uint32_t s2 = !cc ? 0x1032u : r == 381 ? 0x4410u : 0x4444u, s3 = !cc ? 0x1032u : r == 377 ? 0x4410u : 0x4444u;
            uint32_t w[CV_CPB][4];
#pragma unroll
            for (int c = 0; c < CV_CPB; c++) { w[c][0] = E2[512 * c]; w[c][1] = E2[512 * c + 1]; w[c][2] = E3[512 * c]; w[c][3] = E3[512 * c + 1]; }
#pragma unroll
            for (int c = 0; c < CV_CPB; c++) {
                const uint32_t a = __byte_perm(w[c][3], w[c][2], s1), b = __byte_perm(w[c][1], w[c][0], s2);
                *reinterpret_cast<uint4*>(sm + CV_SM_T + c * TAPB + r * 16) =
                    make_uint4(__byte_perm(w[c][1], w[c][0], s0), dd || cc ? a : b, dd || cc ? b : a, __byte_perm(w[c][3], w[c][2], s3));
            }
        }
        TSTAMP1X(12, 256);
        if (layer == 0) {
#pragma unroll
            for (int c = 0; c < CV_CPB; c++) reinterpret_cast<uint4*>(yT + (size_t)(d0 + c) * XCP)[t2] = make_uint4(~0u, ~0u, ~0u, ~0u);
        }
        pdl_sync();
        if (layer && blockIdx.x == 0 && t2 == 0) g_epoch = ld_epoch();
    } else {
        const uint4* ppv = piv + tid;
        const float4* psv = sum + tid;
        const uint2* pxv = reinterpret_cast<const uint2*>(x1T + (size_t)d0 * XCP) + (tid >> 4) * 32 + (tid & 15);
        asm volatile("st.shared.u64 [%0], %1;" ::"r"(smem_u32(Ys) + tid * 8), "l"((uint64_t)ppv ^ (uint64_t)psv ^ (uint64_t)pxv) : "memory");
        pdl_sync();
        SPAN(3 + 4 * layer, 1);
        TSTAMP(0);
        if (threadIdx.x == 0) { GSTAMP(g_tim, 15); }
        float4 sv[4];
#pragma unroll
        for (int k = 0; k < 4; k++) sv[k] = CV_LD(psv + 256 * k);
        const uint4 pv = CV_LD(ppv);
        uint2 xe[CV_CPB], xo[CV_CPB];
#pragma unroll
        for (int c = 0; c < CV_CPB; c++) { xe[c] = CV_LDX(pxv + c * (XCP / 4)); xo[c] = CV_LDX(pxv + c * (XCP / 4) + 16); }
        uint32_t mw[4];
        float rs[8];
#pragma unroll
        for (int k = 0; k < 4; k++) {
            const uint32_t pw = k == 0 ? pv.x : k == 1 ? pv.y : k == 2 ? pv.z : pv.w;
            const float d0_ = sv[k].x * (1.0f / DM), d1_ = sv[k].z * (1.0f / DM);
            mw[k] = pack2(__uint_as_float(pw << 16) + d0_, __uint_as_float(pw & 0xffff0000u) + d1_);
            const uint32_t vr = pack2(fmaxf(fmaf(-d0_, d0_, sv[k].y * (1.0f / DM)), 0.f), fmaxf(fmaf(-d1_, d1_, sv[k].w * (1.0f / DM)), 0.f));
            const uint32_t ve = pack2(__uint_as_float(vr << 16) + 1e-5f, __uint_as_float(vr & 0xffff0000u) + 1e-5f);
            const uint32_t sd = pack2(sqrt_apx(__uint_as_float(ve << 16)), sqrt_apx(__uint_as_float(ve & 0xffff0000u)));
            rs[2 * k] = rcp_apx(__uint_as_float(sd << 16)); rs[2 * k + 1] = rcp_apx(__uint_as_float(sd & 0xffff0000u));
        }
        if (rs[0] != 123.f) TSTAMP(13);
        const int ch = tid + UPADF / 8, pch = ch ^ ((ch >> 3) & 1);
#pragma unroll
        for (int c = 0; c < CV_CPB; c++) {
            *reinterpret_cast<uint4*>(Xs + c * XLEN + tid * 8) = make_uint4(xe[c].x, xe[c].y, xo[c].x, xo[c].y);
            const uint32_t e0 = sub2(xe[c].x, mw[0]), e1 = sub2(xe[c].y, mw[1]), o0 = sub2(xo[c].x, mw[2]), o1 = sub2(xo[c].y, mw[3]);
            *reinterpret_cast<uint4*>(Us + c * ULEN + pch * 8) =
                make_uint4(pack2(__uint_as_float(e0 << 16) * rs[0], __uint_as_float(o0 << 16) * rs[4]), pack2(__uint_as_float(e0 & 0xffff0000u) * rs[1], __uint_as_float(o0 & 0xffff0000u) * rs[5]),
                           pack2(__uint_as_float(e1 << 16) * rs[2], __uint_as_float(o1 << 16) * rs[6]), pack2(__uint_as_float(e1 & 0xffff0000u) * rs[3], __uint_as_float(o1 & 0xffff0000u) * rs[7]));
        }
    }
    __syncthreads();
    TSTAMP(1);
#pragma unroll 1
    for (int rd = rd0; rd < (int)rd1; rd++) {
        const int i = 32 * rd + lane;
        if (i < CV_CPB * 193) {
            const int c = i / 193, chunk = i - c * 193 - 1, ch = chunk + UPADF / 8;
            const bf16* uc = Us + c * ULEN;
            const uint4 o = *reinterpret_cast<const uint4*>(uc + (ch ^ ((ch >> 3) & 1)) * 8);
            const uint2 lo = *reinterpret_cast<const uint2*>(uc + ((ch - 1) ^ (((ch - 1) >> 3) & 1)) * 8 + 4);
            const uint2 hi = *reinterpret_cast<const uint2*>(uc + ((ch + 1) ^ (((ch + 1) >> 3) & 1)) * 8);
            const uint32_t w[8] = {lo.x, lo.y, o.x, o.y, o.z, o.w, hi.x, hi.y};
            float v[16], b[8];
#pragma unroll
            for (int k = 0; k < 8; k++) { v[2 * k] = __uint_as_float(w[k] << 16); v[2 * k + 1] = __uint_as_float(w[k] & 0xffff0000u); }
            unsigned char* bx = sm + CV_SM_B + c * BX_LEN + chunk * 16;
#pragma unroll
            for (int k = 0; k < 8; k++) b[k] = v[k + 4] + (v[k + 3] + v[k + 5]);
            *reinterpret_cast<uint2*>(bx + BX_3 + 168) = make_uint2(pack2(b[0], b[1]), pack2(b[2], b[3]));
            *reinterpret_cast<uint2*>(bx + BX_3 + 176) = make_uint2(pack2(b[4], b[5]), pack2(b[6], b[7]));
#pragma unroll
            for (int k = 0; k < 8; k++) b[k] += v[k + 2] + v[k + 6];
            *reinterpret_cast<uint4*>(bx + BX_5 + 160) = make_uint4(pack2(b[0], b[1]), pack2(b[2], b[3]), pack2(b[4], b[5]), pack2(b[6], b[7]));
            if (chunk < 128) {
#pragma unroll
                for (int k = 0; k < 8; k++) b[k] += v[k + 1] + v[k + 7];
                *reinterpret_cast<uint4*>(bx + BX_7 + 272) = make_uint4(pack2(b[0], b[1]), pack2(b[2], b[3]), pack2(b[4], b[5]), pack2(b[6], b[7]));
#pragma unroll
                for (int k = 0; k < 8; k++) b[k] += v[k] + v[k + 8];
                *reinterpret_cast<uint4*>(bx + BX_9 + 272) = make_uint4(pack2(b[0], b[1]), pack2(b[2], b[3]), pack2(b[4], b[5]), pack2(b[6], b[7]));
            }
        }
    }
    __syncwarp();
    if (lane == 0) mbar_arrive(smem_u32(sm + CV_SM_CNT) + 96);
    TSTAMP(2);
    {
        float acc[8][4];
#pragma unroll
        for (int j = 0; j < 8; j++)
#pragma unroll
            for (int k = 0; k < 4; k++) acc[j][k] = 0.f;
#pragma unroll 1
        for (int pass = (type == 2 || type == 4) ? 1 : 0; pass < ((type == 1 || type == 3) ? 1 : 2); pass++) {
            const uint32_t o0 = pass ? lds_off[2] : lds_off[0], o1 = pass ? lds_off[3] : lds_off[1];
            if (H) direct_pass<true>(acc, ubase + T0 * 256, o0, o1, Tc + 64 * pass, pass == 0);
            else direct_pass<false>(acc, ubase, o0, o1, Tc + 64 * pass, pass == 0);
        }
        TSTAMP(6);
        mbar_wait(smem_u32(sm + CV_SM_CNT) + 96, 0);
        if (type != 1 && type != 4) {
            const uint32_t* w2 = reinterpret_cast<const uint32_t*>(sm + CV_SM_T + c * TAPB + TAP_W2) + (115 - 96) + 4 * g - 2 * ti;
            uint32_t f[10][2];
#pragma unroll
            for (int k = 0; k < 10; k++) { f[k][0] = w2[16 * k]; f[k][1] = w2[16 * k - 8]; }
            const uint32_t ab = bbase + off2 + (2 * T0 + 6) * 128;
            const int kmax = H ? 23 : 8;
            uint32_t a[3][4];
            ldsm_x4_t(a[0], ab);
            ldsm_x4_t(a[1], ab - 128);
#pragma unroll
            for (int kp = 0; kp < 24; kp++) {
                if (kp > kmax) break;
                if (kp < 22) ldsm_x4_t(a[(kp + 2) % 3], ab - min(kp + 2, kmax) * 128);
#pragma unroll
                for (int j = 0; j < 8; j++) {
                    const int ee = 2 * j - 14 + kp;
                    if (ee >= 0 && ee <= 9) mma_bf16(acc[j], a[kp % 3][0], a[kp % 3][1], a[kp % 3][2], a[kp % 3][3], f[ee][0], f[ee][1]);
                }
            }
        }
        TSTAMP(7);
        if (type != 2 && type != 4) {
            const uint32_t* w3 = reinterpret_cast<const uint32_t*>(sm + CV_SM_T + c * TAPB + TAP_W3) + (129 - 96) + 2 * (g - ti);
            uint32_t f[9][2];
#pragma unroll
            for (int k = 0; k < 9; k++) { f[k][0] = w3[16 * k]; f[k][1] = w3[16 * k - 8]; }
            const uint32_t ab = bbase + off3 + (T0 - 2) * 256;
            uint32_t a[3][4];
            ldsm_x4_t(a[0], ab);
            ldsm_x4_t(a[1], ab - H * 256);
#pragma unroll
            for (int kp = 0; kp < 9; kp++) {
                if (kp > T0) break;
                if (kp < 7) ldsm_x4_t(a[(kp + 2) % 3], ab - min(kp + 2, T0) * 256);
#pragma unroll
                for (int j = 0; j < 8; j++) {
                    const int dl = j - 7 + kp;
                    if (dl >= 0 && dl <= 8) mma_bf16(acc[j], a[kp % 3][0], a[kp % 3][1], a[kp % 3][2], a[kp % 3][3], f[dl][0], f[dl][1]);
                }
            }
            const uint2* Dc = reinterpret_cast<const uint2*>(sm + CV_SM_T + c * TAPB + TAP_C) + e;
            const uint2 h63 = Dc[16], h64 = Dc[32], l63 = Dc[8], l64 = Dc[24];
#pragma unroll
            for (int j = 0; j < 8; j++)
                if (j == 7 || H) {
                    uint32_t bq[4];
                    ldsm_x4(bq, ubase + offc + (T0 + j - 8) * 256);
                    mma_bf16(acc[j], h64.x, h64.y, l64.x, l64.y, bq[0], bq[1]);
                    mma_bf16(acc[j], h63.x, h63.y, l63.x, l63.y, bq[2], bq[3]);
                }
        }
        TSTAMP(8);
        int hh = (0x14 >> type) & 1;
        asm volatile("" : "+r"(hh));
        const bool hi_half = hh;
        if (type != 0) {
            const int pair = H ? c : 5;
            float4* give = reinterpret_cast<float4*>(sm + CV_SM_P + pair * 4096 + (hi_half ? 2048 : 0)) + lane;
            const float4* take = reinterpret_cast<const float4*>(sm + CV_SM_P + pair * 4096 + (hi_half ? 0 : 2048)) + lane;
            const uint32_t pb = smem_u32(sm + CV_SM_CNT) + pair * 16;
#pragma unroll
            for (int j = 0; j < 8; j++)
                asm volatile("{\n.reg .pred p;\nsetp.eq.s32 p, %5, %6;\n@p st.shared.v4.f32 [%0], {%1,%2,%3,%4};\n}"
                             ::"r"(smem_u32(give + 32 * (j & 3))), "f"(acc[j][0]), "f"(acc[j][1]), "f"(acc[j][2]), "f"(acc[j][3]), "r"(hh), "r"(j < 4 ? 1 : 0) : "memory");
            __syncwarp();
            if (lane == 0) mbar_arrive(pb + (hi_half ? 8 : 0));
            mbar_wait(pb + (hi_half ? 0 : 8), 0);
#pragma unroll
            for (int j = 0; j < 4; j++) {
                const float4 v = take[32 * j];
                acc[j][0] = (hi_half ? acc[j + 4][0] : acc[j][0]) + v.x; acc[j][1] = (hi_half ? acc[j + 4][1] : acc[j][1]) + v.y;
                acc[j][2] = (hi_half ? acc[j + 4][2] : acc[j][2]) + v.z; acc[j][3] = (hi_half ? acc[j + 4][3] : acc[j][3]) + v.w;
            }
        }
        const uint32_t dk = __shfl_sync(~0u, (uint32_t)dskr, c) * 0x10001u;
#pragma unroll 1
        for (int rnd = 0; rnd < (type == 0 ? 2 : 1); rnd++) {
            const int Q = 2 * H + (hi_half ? 1 : rnd);
            if (rnd) {
#pragma unroll
                for (int j = 0; j < 4; j++)
#pragma unroll
                    for (int k = 0; k < 4; k++) acc[j][k] = acc[j + 4][k];
            }
            const uint32_t ya = smem_u32(Ys + c * XLEN) + (128 * (4 * Q + (lane >> 4)) + 16 * (lane & 7) + 8 * ((lane >> 3) & 1)) * 2;
#pragma unroll
            for (int j = 0; j < 4; j += 2)
                asm volatile("stmatrix.sync.aligned.m8n8.x4.trans.shared.b16 [%0], {%1,%2,%3,%4};" ::"r"(ya + j * 256),
                             "r"(pack2(acc[j][0], acc[j][1])), "r"(pack2(acc[j][2], acc[j][3])),
                             "r"(pack2(acc[j + 1][0], acc[j + 1][1])), "r"(pack2(acc[j + 1][2], acc[j + 1][3])) : "memory");
            __syncwarp();
            uint4 yv[2], xv[2], uv[2];
#pragma unroll
            for (int k = 0; k < 2; k++) {
                const int t = 512 * Q + 256 * k + 8 * lane, cu = (t + UPADF) >> 3;
                yv[k] = *reinterpret_cast<const uint4*>(Ys + c * XLEN + t);
                xv[k] = *reinterpret_cast<const uint4*>(Xs + c * XLEN + t);
                uv[k] = *reinterpret_cast<const uint4*>(Us + c * ULEN + (cu ^ ((cu >> 3) & 1)) * 8);
            }
#pragma unroll
            for (int k = 0; k < 2; k++) {
                const uint32_t z0 = fin2(yv[k].x, uv[k].x, dk), z1 = fin2(yv[k].y, uv[k].y, dk), z2 = fin2(yv[k].z, uv[k].z, dk), z3 = fin2(yv[k].w, uv[k].w, dk);
                if (layer)
                    asm volatile("st.relaxed.gpu.global.v4.u32 [%0], {%1,%2,%3,%4};" ::"l"(dst + (size_t)(d0 + c) * XCP + 512 * Q + 256 * k + 8 * lane),
                                 "r"(add2(__byte_perm(xv[k].x, xv[k].z, 0x5410), z0)), "r"(add2(__byte_perm(xv[k].x, xv[k].z, 0x7632), z1)),
                                 "r"(add2(__byte_perm(xv[k].y, xv[k].w, 0x5410), z2)), "r"(add2(__byte_perm(xv[k].y, xv[k].w, 0x7632), z3)) : "memory");
                else {
                    uint2* dp = reinterpret_cast<uint2*>(dst + (size_t)(d0 + c) * XCP + 512 * Q + 256 * k) + (lane >> 4) * 32 + (lane & 15);
                    dp[0] = make_uint2(add2(xv[k].x, __byte_perm(z0, z1, 0x5410)), add2(xv[k].y, __byte_perm(z2, z3, 0x5410)));
                    dp[16] = make_uint2(add2(xv[k].z, __byte_perm(z0, z1, 0x7632)), add2(xv[k].w, __byte_perm(z2, z3, 0x7632)));
                }
            }
        }
        TSTAMP(4);
        if (layer == 1) {
            const int mb = blockIdx.x >> 3, cg = blockIdx.x & 7;
            const bf16* src = dst + (size_t)(cg * 80 + (tid >> 4)) * XCP + mb * 128 + (tid & 15) * 8;
            uint32_t v[3][4];
            __syncthreads();
            TSTAMP(5);
            uint32_t todo = warp < 8 ? 7 : 3;
#pragma unroll 1
            for (int it = 0; it < SPIN_MAX; it++) {
#pragma unroll
                for (int k = 0; k < 3; k++)
                    if (todo >> k & 1)
                        asm volatile("ld.relaxed.gpu.global.v4.u32 {%0,%1,%2,%3}, [%4];" : "=r"(v[k][0]), "=r"(v[k][1]), "=r"(v[k][2]), "=r"(v[k][3]) : "l"(src + k * (32 * XCP)) : "memory");
#pragma unroll
                for (int k = 0; k < 3; k++)
                    if ((todo >> k & 1) && v[k][0] != ~0u && v[k][1] != ~0u && v[k][2] != ~0u && v[k][3] != ~0u) {
                        *reinterpret_cast<uint4*>(sm + (32 * k + (tid >> 4)) * 272 + (tid & 15) * 16) = make_uint4(v[k][0], v[k][1], v[k][2], v[k][3]);
                        todo ^= 1u << k;
                    }
                if (!todo) break;
                __nanosleep(CV_SLEEP);
            }
            __syncthreads();
            uint32_t w[12];
#pragma unroll
            for (int k = 0; k < 3; k++) ldsm_x4(&w[4 * k], smem_u32(sm) + min(32 * k + lane, 79) * 272 + warp * 16);
            const uint32_t ot = smem_u32(sm + CV_SM_O) + warp * 1280, oa = ot + (lane & 7) * 160 + (lane >> 3) * 16;
            stsm_x4_t(oa, w[0], w[1], w[2], w[3]);
            stsm_x4_t(oa + 64, w[4], w[5], w[6], w[7]);
            asm volatile("stmatrix.sync.aligned.m8n8.x2.trans.shared.b16 [%0], {%1,%2};" ::"r"(oa + 128), "r"(w[8]), "r"(w[9]) : "memory");
            fence_async_smem();
            __syncwarp();
            if (lane == 0) tma_store_2d(&tmOut, cg * 80, mb * 128 + 8 * warp, ot);
        }
    }
    TSTAMP(3);
    GSTAMP(g_tim, 14);
    SPAN(3 + 4 * layer, 3);
}

__device__ __forceinline__ void wgmma_fence() { asm volatile("wgmma.fence.sync.aligned;" ::: "memory"); }
__device__ __forceinline__ void wgmma_commit() { asm volatile("wgmma.commit_group.sync.aligned;" ::: "memory"); }
template <int N> __device__ __forceinline__ void wgmma_wait() { asm volatile("wgmma.wait_group.sync.aligned %0;" ::"n"(N) : "memory"); }
__device__ __forceinline__ uint64_t make_desc(uint32_t addr, uint32_t lbo, uint32_t sbo, uint32_t mode) {
    return (uint64_t)((addr & 0x3FFFF) >> 4) | ((uint64_t)(lbo >> 4) << 16) | ((uint64_t)(sbo >> 4) << 32) | ((uint64_t)mode << 62);
}
template <int TA, int TB>
__device__ __forceinline__ void wgmma_n240(float (&d)[120], uint64_t da, uint64_t db, int acc) {
    asm volatile("{\n.reg .pred p;\nsetp.ne.b32 p, %124, 0;\nwgmma.mma_async.sync.aligned.m64n240k16.f32.bf16.bf16 {%0,%1,%2,%3,%4,%5,%6,%7,%8,%9,%10,%11,%12,%13,%14,%15,%16,%17,%18,%19,%20,%21,%22,%23,%24,%25,%26,%27,%28,%29,%30,%31,%32,%33,%34,%35,%36,%37,%38,%39,%40,%41,%42,%43,%44,%45,%46,%47,%48,%49,%50,%51,%52,%53,%54,%55,%56,%57,%58,%59,%60,%61,%62,%63,%64,%65,%66,%67,%68,%69,%70,%71,%72,%73,%74,%75,%76,%77,%78,%79,%80,%81,%82,%83,%84,%85,%86,%87,%88,%89,%90,%91,%92,%93,%94,%95,%96,%97,%98,%99,%100,%101,%102,%103,%104,%105,%106,%107,%108,%109,%110,%111,%112,%113,%114,%115,%116,%117,%118,%119}, %120, %121, p, 1, 1, %122, %123;\n}"
                 : "+f"(d[0]), "+f"(d[1]), "+f"(d[2]), "+f"(d[3]), "+f"(d[4]), "+f"(d[5]), "+f"(d[6]), "+f"(d[7]), "+f"(d[8]), "+f"(d[9]), "+f"(d[10]), "+f"(d[11]), "+f"(d[12]), "+f"(d[13]), "+f"(d[14]), "+f"(d[15]), "+f"(d[16]), "+f"(d[17]), "+f"(d[18]), "+f"(d[19]), "+f"(d[20]), "+f"(d[21]), "+f"(d[22]), "+f"(d[23]), "+f"(d[24]), "+f"(d[25]), "+f"(d[26]), "+f"(d[27]), "+f"(d[28]), "+f"(d[29]), "+f"(d[30]), "+f"(d[31]), "+f"(d[32]), "+f"(d[33]), "+f"(d[34]), "+f"(d[35]), "+f"(d[36]), "+f"(d[37]), "+f"(d[38]), "+f"(d[39]), "+f"(d[40]), "+f"(d[41]), "+f"(d[42]), "+f"(d[43]), "+f"(d[44]), "+f"(d[45]), "+f"(d[46]), "+f"(d[47]), "+f"(d[48]), "+f"(d[49]), "+f"(d[50]), "+f"(d[51]), "+f"(d[52]), "+f"(d[53]), "+f"(d[54]), "+f"(d[55]), "+f"(d[56]), "+f"(d[57]), "+f"(d[58]), "+f"(d[59]), "+f"(d[60]), "+f"(d[61]), "+f"(d[62]), "+f"(d[63]), "+f"(d[64]), "+f"(d[65]), "+f"(d[66]), "+f"(d[67]), "+f"(d[68]), "+f"(d[69]), "+f"(d[70]), "+f"(d[71]), "+f"(d[72]), "+f"(d[73]), "+f"(d[74]), "+f"(d[75]), "+f"(d[76]), "+f"(d[77]), "+f"(d[78]), "+f"(d[79]), "+f"(d[80]), "+f"(d[81]), "+f"(d[82]), "+f"(d[83]), "+f"(d[84]), "+f"(d[85]), "+f"(d[86]), "+f"(d[87]), "+f"(d[88]), "+f"(d[89]), "+f"(d[90]), "+f"(d[91]), "+f"(d[92]), "+f"(d[93]), "+f"(d[94]), "+f"(d[95]), "+f"(d[96]), "+f"(d[97]), "+f"(d[98]), "+f"(d[99]), "+f"(d[100]), "+f"(d[101]), "+f"(d[102]), "+f"(d[103]), "+f"(d[104]), "+f"(d[105]), "+f"(d[106]), "+f"(d[107]), "+f"(d[108]), "+f"(d[109]), "+f"(d[110]), "+f"(d[111]), "+f"(d[112]), "+f"(d[113]), "+f"(d[114]), "+f"(d[115]), "+f"(d[116]), "+f"(d[117]), "+f"(d[118]), "+f"(d[119])
                 : "l"(da), "l"(db), "n"(TA), "n"(TB), "r"(acc));
}

__device__ __forceinline__ void wgmma_n80(float (&d)[40], uint64_t da, uint64_t db, int acc) {
    asm volatile("{\n.reg .pred p;\nsetp.ne.b32 p, %42, 0;\nwgmma.mma_async.sync.aligned.m64n80k16.f32.bf16.bf16 {%0,%1,%2,%3,%4,%5,%6,%7,%8,%9,%10,%11,%12,%13,%14,%15,%16,%17,%18,%19,%20,%21,%22,%23,%24,%25,%26,%27,%28,%29,%30,%31,%32,%33,%34,%35,%36,%37,%38,%39}, %40, %41, p, 1, 1, 0, 0;\n}"
                 : "+f"(d[0]), "+f"(d[1]), "+f"(d[2]), "+f"(d[3]), "+f"(d[4]), "+f"(d[5]), "+f"(d[6]), "+f"(d[7]), "+f"(d[8]), "+f"(d[9]), "+f"(d[10]), "+f"(d[11]), "+f"(d[12]), "+f"(d[13]), "+f"(d[14]), "+f"(d[15]), "+f"(d[16]), "+f"(d[17]), "+f"(d[18]), "+f"(d[19]), "+f"(d[20]), "+f"(d[21]), "+f"(d[22]), "+f"(d[23]), "+f"(d[24]), "+f"(d[25]), "+f"(d[26]), "+f"(d[27]), "+f"(d[28]), "+f"(d[29]), "+f"(d[30]), "+f"(d[31]), "+f"(d[32]), "+f"(d[33]), "+f"(d[34]), "+f"(d[35]), "+f"(d[36]), "+f"(d[37]), "+f"(d[38]), "+f"(d[39])
                 : "l"(da), "l"(db), "r"(acc));
}

constexpr int A1_THREADS = 384;
constexpr int A1_NST = 4;
#define A1_SKEW 8
constexpr int A1_STAGE = 16384 + WQ_STAGE;
constexpr int A1_KVP = 336;
constexpr int A1_SM_KV = 2 * A1_STAGE;
constexpr int A1_SM_BAR = A1_NST * A1_STAGE;
constexpr int A1_SM_RS = A1_SM_BAR + 512;
constexpr int A1_SM_W0 = A1_SM_BAR + 3072, A1_SM_W3 = A1_SM_BAR - 3 * WOB, A1_SM_A1 = 2 * WOB, A1_SM_A0 = A1_SM_A1 + 61440;
constexpr int A1_SM_XA = A1_SM_W0 + 2 * WOB, A1_SM_XB = A1_SM_XA + 2048;
constexpr int A1_SMEM = A1_SM_W0 + 3 * WOB;
static_assert(A1_SM_W3 >= A1_SM_KV + 144 * A1_KVP && A1_SM_W3 % 128 == 0 && A1_SM_A1 % 1024 == 0 && A1_SM_A0 <= A1_SM_KV && A1_SM_A0 + 61440 <= A1_SM_W3 && A1_SMEM <= 232448, "layout");
__device__ __forceinline__ constexpr uint32_t wo_off(int h) { return h * WOB + (h < 3 ? A1_SM_W0 : h < 6 ? A1_SM_W3 - 3 * WOB : -6 * WOB); }
#define A1_FRED "red.relaxed.gpu.global.add.u32"
#define A1_FLD "ld.acquire.gpu.global.u32"
#define ST_SLEEP 20
#define ST_SLEEP0 300
#define WO_LATE bar_done
#define A1_P0 2
#define A1_PW (kb - 2)
#define A1_FSPIN SPIN_MAX
#define A1_FSLEEP 40
#define A1_WOAT 6

template <int L>
__device__ __forceinline__ void a1_mainloop(float (&acc)[120], uint32_t sbase, uint32_t bars, int wg, int tile) {
    constexpr int layer = L; (void)layer;
    const uint64_t da0 = L ? make_desc(sbase + wg * 8192, 8192, 1024, 1) : make_desc(sbase + wg * 8192, 16, 1024, 1), db0 = make_desc(sbase + 16384, 16, 1024, 1);
#pragma unroll 1
    for (int t = 0;; t++) {
        const int st = t % A1_NST;
        mbar_wait(bars + 8 * st, (t / A1_NST) & 1);
        if (t == A1_SKEW && wg == 0) mbar_wait(bars + 160, 0);
        TSTAMP3(1 + t);
        wgmma_fence();
#pragma unroll
        for (int kk = 0; kk < 4; kk++) wgmma_n240<L, 0>(acc, da0 + (uint32_t)(st * (A1_STAGE / 16) + kk * (L ? 128 : 2)), db0 + (uint32_t)(st * (A1_STAGE / 16) + kk * 2), kk ? 1 : t);
        wgmma_commit();
        if (t == 9) break;
        if (t == A1_SKEW - 1 && wg == 0) wgmma_wait<0>(); else wgmma_wait<1>();
        if (t > 0 && (threadIdx.x & 127) == 0) {
            if (t != A1_SKEW || wg) mbar_arrive(bars + 8 * (A1_NST + (t - 1) % A1_NST));
            if (t == A1_SKEW - 1 && wg == 0) mbar_arrive(bars + 8 * (A1_NST + t % A1_NST));
        }
    }
}

__global__ void __launch_bounds__(A1_THREADS, 1) a1_kernel(const int layer, const bf16* __restrict__ x0, const unsigned char* __restrict__ wq, const unsigned char* __restrict__ wo,
                                                           float2* __restrict__ rsum, uint4* __restrict__ of, const __grid_constant__ CUtensorMap tmX,
                                                           const __grid_constant__ CUtensorMap tmR, const __grid_constant__ CUtensorMap tmX1, const __grid_constant__ TileTab tab) {
    extern __shared__ __align__(1024) unsigned char stg[];
    const uint32_t sbase = smem_u32(stg);
    const uint32_t bars = sbase + A1_SM_BAR;
    const uint32_t bar_stat = bars + 64, bar_kv = bars + 72, bar_rd = bars + 168;
    const uint32_t bar_wo = bars + 208, bar_done = bars + 216, bar_pv = bars + 224, bar_kvf = bars + 232, bar_f2 = bars + 248, bar_e2 = bars + 384, que = bars + 448;
    const int tid = threadIdx.x;
    const int w = __shfl_sync(~0u, tid >> 5, 0), wg = w >> 2;
    uint32_t smid, ns;
    asm volatile("mov.u32 %0, %smid;" : "=r"(smid));
    asm volatile("mov.u32 %0, %nsmid;" : "=r"(ns));
    const auto te = tab.e[ns == tab.ns ? smid : 132 + blockIdx.x];
    const int tile = te.tile, mb = te.mb, hg = te.hg;
    float2* rst = reinterpret_cast<float2*>(stg + A1_SM_RS) + 8;
    auto issue_w = [&](int it) { bulk_load(sbase + (it % A1_NST) * A1_STAGE + 16384, wq + te.woff + it * WQ_STAGE, WQ_STAGE, bars + 8 * (it % A1_NST)); };
    auto issue_x = [&](int it, int kb) {
        asm volatile("cp.async.bulk.tensor.5d.shared::cluster.global.mbarrier::complete_tx::bytes [%0], [%1, {%3, %3, %3, %4, %5}], [%2];"
                     ::"r"(sbase + (it % A1_NST) * A1_STAGE), "l"(&tmX), "r"(bars + 8 * (it % A1_NST)), "r"(0), "r"(mb), "r"(kb) : "memory");
    };
    if (w == 8 && tile < 128) {
        const bool one = elect();
        if (one) {
#pragma unroll
            for (int i = 0; i < A1_NST; i++) mbar_init(bars + 8 * i, 1);
            asm volatile("fence.mbarrier_init.release.cluster;" ::: "memory");
        }
        __syncwarp();
        asm volatile("bar.arrive 0, 384;" ::: "memory");
        if (one) {
#define PW asm volatile("griddepcontrol.wait;" ::: "memory");
            if (layer) { issue_w(0); PW issue_x(0, te.kb0); issue_x(1, te.kb0 + 1); }
            else { issue_x(0, te.kb0); issue_x(1, te.kb0 + 1); PW issue_w(0); }
            issue_w(1);
#pragma unroll
            for (int i = 0; i < A1_NST; i++) mbar_expect_tx(bars + 8 * i, A1_STAGE);
            asm volatile("griddepcontrol.launch_dependents;" ::: "memory");
#pragma unroll
            for (int kb = 2; kb < A1_P0; kb++) { issue_x(kb, te.kb0 + kb); issue_w(kb); }
            DBGC(34); DBGV(40, t_entry); DBGV(30, t_a); DBGV(31, t_b); DBGV(32, t_c); DBGV(38, t_d); DBGV(39, t_e);
        }
    }
    if (tile >= 128) { sm_idle(layer); return; }
    if (wg == 2) {
        if (w != 8) {
            if (tid == 320) { prefetch_tmap(&tmX); prefetch_tmap(&tmR); prefetch_tmap(&tmX1); }
            asm volatile("bar.sync 0, 384;" ::: "memory");
        }
        if (w == 9) {
            asm volatile("bar.arrive 3, 64;" ::: "memory");
            if (layer == 0) pdl_sync();
            float4 a[2] = {};
#pragma unroll
            for (int k = 0; k < 10; k++)
#pragma unroll
                for (int h = 0; h < 2; h++) {
                    const float4 v = __ldcg(reinterpret_cast<const float4*>(g_csp + k * 1920 + hg * 240) + min(tid - 288 + 32 * h, 59));
                    a[h].x += v.x; a[h].y += v.y; a[h].z += v.z; a[h].w += v.w;
                }
#pragma unroll
            for (int h = 0; h < 2; h++)
#pragma unroll
                for (int k = 0; k < 4; k++) {
                    const float c = 0.5f * (k == 0 ? a[h].x : k == 1 ? a[h].y : k == 2 ? a[h].z : a[h].w), c1 = c - rbf(c), c2 = c1 - rbf(c1);
                    *reinterpret_cast<uint4*>(stg + A1_SM_XB + (4 * min(tid - 288 + 32 * h, 59) + k) * 16) = make_uint4(pack2(c, c1), pack2(c2, 0.f), 0u, 0u);
                }
            fence_async_smem();
            __syncwarp();
            if (tid == 288) mbar_arrive(bar_stat);
#pragma unroll 4
            for (int k = 0; k < 40; k++) asm volatile("st.global.v4.u32 [%0], {%1,%1,%1,%1};" ::"l"(of + (mb * 8 + hg) * 1280 + 32 * k + (tid - 288)), "r"(~0u) : "memory");
            asm volatile("fence.acq_rel.gpu;" ::: "memory");
            asm volatile("fence.proxy.async.global;" ::: "memory");
            __syncwarp();
            if (tid == 288) mbar_arrive(bar_done);
            TSTAMP1T(9, 288);
        } else if (w == 8) {
            asm volatile("bar.sync 3, 64;" ::: "memory");
            if (elect()) {
#pragma unroll 1
                for (int kb = A1_P0; kb < 10; kb++) {
                    if (kb < A1_NST) mbar_wait(bars + 8 * A1_PW, 0);
                    else {
                        mbar_wait(bars + 8 * (A1_NST + kb % A1_NST), ((kb / A1_NST) - 1) & 1);
                        if (layer && kb < 9) mbar_wait(bar_rd + 8 * (kb - A1_NST), 0);
                        mbar_expect_tx(bars + 8 * (kb % A1_NST), A1_STAGE);
                    }
                    issue_x(kb, kb < 5 ? kb + te.kb0 : kb - te.kb0); issue_w(kb);
                    if (kb == A1_WOAT) {
                        mbar_expect_tx(bar_wo, 8 * WOB);
                        bulk_load(sbase + A1_SM_W0, wo + hg * 8 * WOB, 2 * WOB, bar_wo);
                    }
                }
                TSTAMP1T(6, 256);
                mbar_wait(bars + 8 * (A1_NST + 3), 1);
                bulk_load(sbase + A1_SM_W3, wo + (hg * 8 + 3) * WOB, 3 * WOB, bar_wo);
            }
            __syncwarp();
        } else {
            const int j = tid - 320;
            const uint32_t tag = ld_epoch();
            if (tid == 352) sm_started(layer);
            if (layer == 0) {
                const uint4* src = reinterpret_cast<const uint4*>(x0 + (size_t)(mb * 128 + hg * 16 + (j >> 2)) * DM);
                uint4 v[20];
#pragma unroll
                for (int k = 0; k < 20; k++) v[k] = __ldg(src + (j & 3) + 4 * k);
                const float p0 = __uint_as_float(__shfl_sync(~0u, v[0].x, j & 28) << 16);
                float s[2] = {0.f, 0.f}, q[2] = {0.f, 0.f};
#pragma unroll
                for (int k = 0; k < 20; k++) {
                    const uint32_t w[4] = {v[k].x, v[k].y, v[k].z, v[k].w};
#pragma unroll
                    for (int i = 0; i < 4; i++) {
                        const float a = __uint_as_float(w[i] << 16) - p0, b = __uint_as_float(w[i] & 0xffff0000u) - p0;
                        s[0] += a; s[1] += b; q[0] = fmaf(a, a, q[0]); q[1] = fmaf(b, b, q[1]);
                    }
                }
                float s0 = s[0] + s[1], q0 = q[0] + q[1];
#pragma unroll
                for (int o = 1; o <= 2; o <<= 1) { s0 += __shfl_xor_sync(~0u, s0, o); q0 += __shfl_xor_sync(~0u, q0, o); }
                if ((j & 3) == 0) {
                    const float d = s0 * (1.0f / DM);
                    const uint32_t ms = pack2(p0 + d, sqrt_apx(rbf(rbf(fmaxf(fmaf(-d, d, q0 * (1.0f / DM)), 0.f)) + 1e-5f)));
                    asm volatile("st.global.cg.u64 [%0], %1;" ::"l"(g_rstat + mb * 128 + (j & 4) * 16 + hg * 8 + (j >> 3)), "l"(tagw(ms, tag)) : "memory");
                    g_piv[mb * 128 + hg * 16 + ((j >> 2) & 8) + (j & 4) + ((j >> 3) & 3)] = __ushort_as_bfloat16((unsigned short)ms);
                }
            }
            float o[4];
            int row;
            if (layer == 0) {
                ulonglong2 v;
#pragma unroll 1
                for (int it = 0; it < SPIN_MAX; it++) {
                    v = ld_tag2(reinterpret_cast<const ulonglong2*>(g_rstat + mb * 128) + j);
                    if (tag_ok(v, tag)) break;
                    __nanosleep(100);
                }
                o[0] = __uint_as_float((uint32_t)v.x << 16); o[1] = rcp_apx(__uint_as_float((uint32_t)v.x & 0xffff0000u));
                o[2] = __uint_as_float((uint32_t)v.y << 16); o[3] = rcp_apx(__uint_as_float((uint32_t)v.y & 0xffff0000u));
                row = 2 * j;
            } else {
                const int ch = j & 7, kg = (j >> 3) & 3;
                const unsigned char* src = stg + (j >> 5) * 8192 + (hg & 3) * 2048;
                float s[8], q[8], p0[8];
#pragma unroll
                for (int i = 0; i < 8; i++) { s[i] = 0.f; q[i] = 0.f; }
#pragma unroll 1
                for (int it = 0; it < 5; it++) {
                    uint4 v[4];
                    mbar_wait(bars + 8 * (it % A1_NST), it / A1_NST);
#pragma unroll
                    for (int k = 0; k < 4; k++) v[k] = *reinterpret_cast<const uint4*>(src + (it % A1_NST) * A1_STAGE + (4 * k + kg) * 128 + ((ch ^ ((4 * k + kg) & 7)) << 4));
                    if (it == 0) {
                        const uint4 pv = *reinterpret_cast<const uint4*>(src + (ch << 4));
                        const uint32_t w[4] = {pv.x, pv.y, pv.z, pv.w};
#pragma unroll
                        for (int i = 0; i < 4; i++) { p0[2 * i] = __uint_as_float(w[i] << 16); p0[2 * i + 1] = __uint_as_float(w[i] & 0xffff0000u); }
                    }
                    asm volatile("" :: "r"(v[0].x), "r"(v[1].x), "r"(v[2].x), "r"(v[3].x), "f"(p0[0]) : "memory");
                    __syncwarp();
                    if ((tid & 31) == 0) mbar_arrive(bar_rd + 8 * it);
#pragma unroll
                    for (int k = 0; k < 4; k++) {
                        const uint32_t w[4] = {v[k].x, v[k].y, v[k].z, v[k].w};
#pragma unroll
                        for (int i = 0; i < 4; i++) {
                            const float a = __uint_as_float(w[i] << 16) - p0[2 * i], b = __uint_as_float(w[i] & 0xffff0000u) - p0[2 * i + 1];
                            s[2 * i] += a; s[2 * i + 1] += b; q[2 * i] = fmaf(a, a, q[2 * i]); q[2 * i + 1] = fmaf(b, b, q[2 * i + 1]);
                        }
                    }
                }
#pragma unroll
                for (int i = 0; i < 4; i++) {
                    const bool up = kg & 2;
                    const float ss = __shfl_xor_sync(~0u, up ? s[i] : s[i + 4], 16), qq = __shfl_xor_sync(~0u, up ? q[i] : q[i + 4], 16);
                    s[i] = (up ? s[i + 4] : s[i]) + ss; q[i] = (up ? q[i + 4] : q[i]) + qq; p0[i] = up ? p0[i + 4] : p0[i];
                }
#pragma unroll
                for (int i = 0; i < 2; i++) {
                    const bool up = kg & 1;
                    const float ss = __shfl_xor_sync(~0u, up ? s[i] : s[i + 2], 8), qq = __shfl_xor_sync(~0u, up ? q[i] : q[i + 2], 8);
                    s[i] = (up ? s[i + 2] : s[i]) + ss; q[i] = (up ? q[i + 2] : q[i]) + qq; p0[i] = up ? p0[i + 2] : p0[i];
                }
                uint4* gp = g_halo + 86016 + mb * 512 + j;
                const float d0 = s[0] * (1.0f / 80.0f), d1 = s[1] * (1.0f / 80.0f);
                asm volatile("st.relaxed.gpu.global.v4.f32 [%0], {%1,%2,%3,%4};" ::"l"(gp + hg * 64), "f"(p0[0] + d0), "f"(fmaxf(fmaf(-d0, s[0], q[0]), 0.f)), "f"(p0[1] + d1), "f"(fmaxf(fmaf(-d1, s[1], q[1]), 0.f)) : "memory");
                __nanosleep(ST_SLEEP0);
                uint32_t pw[8][4], todo = 0xff;
#pragma unroll 1
                for (int it = 0; it < SPIN_MAX; it++) {
#pragma unroll
                    for (int k = 0; k < 8; k++)
                        if (todo >> k & 1) asm volatile("ld.relaxed.gpu.global.v4.u32 {%0,%1,%2,%3}, [%4];" : "=r"(pw[k][0]), "=r"(pw[k][1]), "=r"(pw[k][2]), "=r"(pw[k][3]) : "l"(gp + k * 64) : "memory");
#pragma unroll
                    for (int k = 0; k < 8; k++)
                        if (__all_sync(~0u, pw[k][0] != ~0u && pw[k][1] != ~0u && pw[k][2] != ~0u && pw[k][3] != ~0u)) todo &= ~(1u << k);
                    if (!todo) break;
                    __nanosleep(ST_SLEEP);
                }
#pragma unroll
                for (int r = 0; r < 2; r++) {
                    float mean = 0.f, m2 = 0.f;
#pragma unroll
                    for (int k = 0; k < 8; k++) mean += __uint_as_float(pw[k][2 * r]);
                    mean *= 0.125f;
#pragma unroll
                    for (int k = 0; k < 8; k++) {
                        const float dm = __uint_as_float(pw[k][2 * r]) - mean;
                        m2 += fmaf(80.0f * dm, dm, __uint_as_float(pw[k][2 * r + 1]));
                    }
                    o[2 * r] = rbf(mean);
                    o[2 * r + 1] = rcp_apx(rbf(sqrt_apx(rbf(rbf(m2 * (1.0f / DM)) + 1e-5f))));
                }
                row = (j >> 5) * 64 + (j & 7) * 8 + ((j >> 3) & 3) * 2;
                if (hg == 0) *reinterpret_cast<uint32_t*>(g_piv + SEQ + mb * 128 + 2 * (row & 60) + 4 * (row >> 6) + (row & 3)) = __byte_perm(__float_as_uint(o[0]), __float_as_uint(o[2]), 0x7632);
            }
#pragma unroll
            for (int r = 0; r < 2; r++)
                *reinterpret_cast<uint4*>(stg + A1_SM_XA + (row + r) * 16) = make_uint4(__byte_perm(__float_as_uint(-o[2 * r]), 0, 0x3232), __float_as_uint(-o[2 * r]) >> 16, 0u, 0u);
            *reinterpret_cast<float4*>(rst + row + (row >> 6) * 8) = make_float4(o[0], o[1], o[2], o[3]);
            fence_async_smem();
            TSTAMP1T(7, 320);
            if (tid == 320) DBGC(44);
            __syncwarp();
            if ((tid & 31) == 0) mbar_arrive(bar_stat);
        }
        if (tid == 320) DBGCAL(0);
        if (tid == 352) {
            mbar_wait(WO_LATE, 0);
            mbar_wait(bar_done, 0);
            bulk_load(sbase, wo + (hg * 8 + 6) * WOB, 2 * WOB, bar_wo);
            bulk_load(sbase + A1_SM_W0 + 2 * WOB, wo + (hg * 8 + 2) * WOB, WOB, bar_wo);
        }
        if (w < 10) {
            const int cw = w - 8;
            const uint32_t* fl = reinterpret_cast<const uint32_t*>(rsum + 2 * SEQ) + (((layer * 16 + mb) * 2 + cw) * 8 + (tid & 7)) * FSTR;
            const unsigned char* src = reinterpret_cast<const unsigned char*>(of) + mb * 163840 + cw * 10240 + (tid & 7) * 20480;
            const uint32_t sl = sbase + (cw ? A1_SM_A1 : A1_SM_A0);
            mbar_wait(cw ? bar_done : bar_kvf, 0);
            if ((tid & 31) == 0) {
                mbar_expect_tx(bar_f2 + 64 * cw + 64, 10240);
                tma_load_3d(sl + 51200, &tmR, layer ? 0 : hg * 80, layer ? hg * 80 : mb * 64, layer ? mb * 2 + cw : cw, bar_f2 + 64 * cw + 64);
            }
            __syncwarp();
            uint32_t pend = 0xffu & ~(1u << hg), v = 0;
            const uint32_t bo = wo_off((tid & 7) + ((tid & 7) < hg)) >> 4, lt = (1u << (tid & 31)) - 1;
#pragma unroll 1
            for (int it = 0; pend && it < 2 * SPIN_MAX; it++) {
                if (v != 4 && (pend >> (tid & 31) & 1)) asm volatile(A1_FLD " %0, [%1];" : "=r"(v) : "l"(fl) : "memory");
                uint32_t fr;
                asm volatile("{\n.reg .pred p;\nmbarrier.test_wait.parity.shared::cta.b64 p, [%1], 0;\nselp.b32 %0, 1, 0, p;\n}" : "=r"(fr) : "r"(bar_e2 + 16 * cw + (tid & 1) * 8) : "memory");
                fr = __ballot_sync(~0u, fr);
                uint32_t m = __ballot_sync(~0u, v == 4 || it >= A1_FSPIN) & pend;
                const int q = 8 - __popc(pend) + __popc(m & lt);
                m &= __ballot_sync(~0u, q < ((fr & 2) ? 8 : (fr & 1) ? 7 : 5));
                pend ^= m;
                if (m >> (tid & 31) & 1) DBGC(12 + cw * 8 + (tid & 7));
                if (!m) __nanosleep(A1_FSLEEP);
                else asm volatile("fence.proxy.async.global;" ::: "memory");
                if (m >> (tid & 31) & 1) {
                    bulk_load(q == 7 && !cw ? sbase + A1_SM_W0 : sl + (q < 6 ? q : q - 6) * 10240, src, 10240, bar_f2 + 64 * cw + 8 * q);
                    asm volatile("st.shared.u32 [%0], %1;" ::"r"(que + 32 * cw + 4 * q), "r"(bo) : "memory");
                    mbar_expect_tx(bar_f2 + 64 * cw + 8 * q, 10240);
                    DBGC(44 + cw * 8 + q);
                }
                __syncwarp();
            }
        }
    } else {
        if (tid == 0) {
            mbar_init(bar_stat, 3);
#pragma unroll
            for (int i = 0; i < 8; i++) mbar_init(bar_kv + 8 * i, 1);
            mbar_init(bars + 144, 1);
            mbar_init(bars + 160, 1);
#pragma unroll
            for (int i = 0; i < 5; i++) mbar_init(bar_rd + 8 * i, 2);
            asm volatile("fence.mbarrier_init.release.cluster;" ::: "memory");
        } else if (tid == 32) {
            mbar_init(bar_wo, 1); mbar_init(bar_done, 3); mbar_init(bar_pv, 4); mbar_init(bar_kvf, 8); mbar_init(bars + 240, 4);
#pragma unroll
            for (int i = 0; i < 4; i++) { mbar_init(bar_e2 + 8 * i, i == 1 ? 2 : 1); mbar_init(bars + 8 * (A1_NST + i), 2); }
            asm volatile("fence.mbarrier_init.release.cluster;" ::: "memory");
        } else if (tid == 64) {
#pragma unroll
            for (int i = 1; i <= 16; i++) mbar_init(bar_f2 + 8 * i, 1);
            asm volatile("fence.mbarrier_init.release.cluster;" ::: "memory");
        }
        asm volatile("bar.sync 0, 384;" ::: "memory");
        SPAN(1 + 4 * layer, 0);
        constexpr int on = 1;
        float acc[120];
        const int lane = tid & 31, warp = w & 7, g = lane >> 2, t = lane & 3;
        if (on) {
            SPAN(1 + 4 * layer, 1);
            TSTAMP1(0);
            if (threadIdx.x == 0) { GSTAMP(g_tim1, 15); }
            TSTAMP3(0);
            if (tid == 0) TSTAMP2(0);
            TSTAMP4(0);
            if (tid == 0) DBGC(60);
            if (layer == 0) a1_mainloop<0>(acc, sbase, bars, wg, tile); else a1_mainloop<1>(acc, sbase, bars, wg, tile);
            uint32_t ok;
            asm volatile("{\n.reg .pred p;\nmbarrier.test_wait.parity.shared::cta.b64 p, [%1], 0;\nselp.b32 %0, 1, 0, p;\n}" : "=r"(ok) : "r"(bar_stat) : "memory");
            if (tid == 128 && !ok) mbar_arrive(bars + 160);
            __syncwarp();
            mbar_wait(bar_stat, 0);
            wgmma_fence();
            wgmma_n240<0, 0>(acc, make_desc(sbase + A1_SM_XA + wg * 1024, 0, 128, 0), make_desc(sbase + A1_SM_XB, 0, 128, 0), 1);
            wgmma_commit();
            if (tid == 128 && ok) mbar_arrive(bars + 160);
            mbar_wait(bars + 8 * (A1_NST + 3), 1);
        }
        const float2* rw = rst + 16 * warp + 8 * wg;
        const float rb0 = rw[g + 8].y, ra = rw[g].y * 0.22360679774997896f, rb = rb0 * 0.22360679774997896f;
        wgmma_wait<0>();
        if ((tid & 127) == 0) mbar_arrive(bar_done);
        TSTAMP1(2);
        TSTAMP1T(13, 224);
        if ((tid & 127) == 0) DBGC(62 - wg);
        uint32_t f[2][30];
#pragma unroll
        for (int j = 10; j < 30; j++) f[1][j] = pack2(acc[4 * j + 2], acc[4 * j + 3]);
        if ((warp & 3) == 3) {
            uint4* hout = g_halo + (((layer * 16 + mb) * 8 + hg) * 2 + wg) * 168;
#pragma unroll
            for (int j = 0; j < 20; j += 4)
                asm volatile("st.relaxed.gpu.global.v4.u32 [%0], {%1,%2,%3,%4};" ::"l"(hout + 8 * j + lane), "r"(f[1][10 + j]), "r"(f[1][11 + j]), "r"(f[1][12 + j]), "r"(f[1][13 + j]) : "memory");
            if (t == 0) asm volatile("st.relaxed.gpu.global.f32 [%0], %1;" ::"l"(reinterpret_cast<float*>(hout + 160) + g), "f"(rb0) : "memory");
        }
        TSTAMP1T(12, 224);
        const uint32_t kvw = sbase + A1_SM_KV + (16 * warp + 8 * wg) * A1_KVP;
        const uint32_t mrow = kvw + (lane & 7) * A1_KVP + (lane >> 3) * 16;
#pragma unroll
        for (int j = 0; j < 20; j += 4) stsm_x4(mrow + 16 * A1_KVP + 16 * j, f[1][10 + j], f[1][11 + j], f[1][12 + j], f[1][13 + j]);
        __syncwarp();
        if (lane == 0 && (warp & 3) != 3) mbar_arrive(bar_kv + 8 * (warp + 1));
#pragma unroll
        for (int j = 0; j < 30; j++) f[0][j] = pack2(acc[4 * j], acc[4 * j + 1]);
        stsm_x4(mrow + 8 * A1_KVP + 160, f[0][20], f[0][21], f[0][22], f[0][23]);
        stsm_x4(mrow + 8 * A1_KVP + 224, f[0][24], f[0][25], f[0][26], f[0][27]);
        asm volatile("stmatrix.sync.aligned.m8n8.x2.shared.b16 [%0], {%1,%2};" ::"r"(mrow + 8 * A1_KVP + 288), "r"(f[0][28]), "r"(f[0][29]) : "memory");
#pragma unroll
        for (int j = 0; j < 10; j++) f[1][j] = pack2(acc[4 * j + 2], acc[4 * j + 3]);
        __syncwarp();
        uint32_t vb[10][2], vp[12], kp[12];
#pragma unroll
        for (int j = 0; j < 10; j += 2) ldsm_x4_t(&vb[j][0], kvw + (8 + (lane & 15)) * A1_KVP + 160 + (lane >> 4) * 16 + 16 * j);
        const bool up0 = 2 * t > g, up1 = 2 * t + 1 > g, edge = (mb | (warp & 3)) == 0;
        float rk[4];
        auto above = [&]() {
            mbar_wait(bar_kv + 8 * warp, 0);
#pragma unroll
            for (int j = 0; j < 12; j += 4) ldsm_x4(&kp[j], mrow + 16 * j);
            rk[0] = rw[2 * t - (up0 ? 8 : 0)].y; rk[1] = rw[2 * t + 1 - (up1 ? 8 : 0)].y;
#pragma unroll
            for (int j = 0; j < 12; j += 4) ldsm_x4_t(&vp[j], mrow + 160 + 16 * j - (j == 8 ? (lane & 16) * 2 : 0));
            __syncwarp();
            if (lane == 0) mbar_arrive(bar_kvf);
        };
        auto halo = [&]() {
            if (lane == 0) mbar_arrive(bar_kvf);
            const uint4* hin = g_halo + (((layer * 16 + mb - 1) * 8 + hg) * 2 + wg) * 168;
            uint32_t hv[22] = {};
            rk[0] = rw[2 * t].y; rk[1] = rw[2 * t + 1].y;
            if (mb > 0) {
#pragma unroll 1
                for (int it = 0; it < SPIN_MAX; it++) {
#pragma unroll
                    for (int k = 0; k < 20; k += 4)
                        asm volatile("ld.relaxed.gpu.global.v4.u32 {%0,%1,%2,%3}, [%4];" : "=r"(hv[k]), "=r"(hv[k + 1]), "=r"(hv[k + 2]), "=r"(hv[k + 3]) : "l"(hin + 8 * k + lane) : "memory");
                    asm volatile("ld.relaxed.gpu.global.v2.u32 {%0,%1}, [%2];" : "=r"(hv[20]), "=r"(hv[21]) : "l"(reinterpret_cast<const uint2*>(hin + 160) + t) : "memory");
                    uint32_t m = max(hv[20], hv[21]);
#pragma unroll
                    for (int k = 0; k < 20; k += 2) m = __vimax3_u32(m, hv[k], hv[k + 1]);
                    if (!__any_sync(~0u, m == ~0u)) break;
                }
            }
            if (tid == 0) mbar_arrive(bars + 144);
            if (lane == 0) DBGC(52 - 16 * wg);
#pragma unroll
            for (int j = 0; j < 10; j++) {
                kp[j] = hv[j];
                asm volatile("movmatrix.sync.aligned.m8n8.trans.b16 %0, %1;" : "=r"(vp[j]) : "r"(hv[10 + j]));
            }
            if (up0) rk[0] = __uint_as_float(hv[20]);
            if (up1) rk[1] = __uint_as_float(hv[21]);
        };
        rk[2] = rw[2 * t + (up0 ? 0 : 8)].y; rk[3] = rw[2 * t + 1 + (up1 ? 0 : 8)].y;
        uint32_t qs[4][2];
#pragma unroll
        for (int h = 0; h < 4; h++) {
            qs[h][0] = (t >> 1) == (h & 1) ? f[0][5 * (h >> 1) + 2] : 0u; qs[h][1] = (t >> 1) == (h & 1) ? f[1][5 * (h >> 1) + 2] : 0u;
            asm volatile("" : "+r"(qs[h][0]), "+r"(qs[h][1]));
        }
#pragma unroll
        for (int j = 0; j < 10; j++) asm volatile("" : "+r"(f[0][j]), "+r"(f[1][j]), "+r"(f[0][10 + j]));
        if (warp & 3) above(); else if (wg) halo();
        TSTAMP1T(10, 64);
        float sc[4][3][4];
#pragma unroll
        for (int h = 0; h < 4; h++) {
            const int jb = 5 * (h >> 1) + 3 * (h & 1), js = 5 * (h >> 1) + 2;
#pragma unroll
            for (int nt = 1; nt < 3; nt++) {
#pragma unroll
                for (int e = 0; e < 4; e++) sc[h][nt][e] = 0.f;
                mma_bf16(sc[h][nt], f[0][jb], f[1][jb], f[0][jb + 1], f[1][jb + 1], f[nt - 1][10 + jb], f[nt - 1][11 + jb]);
                mma_bf16_k8(sc[h][nt], qs[h][0], qs[h][1], f[nt - 1][10 + js]);
            }
        }
        if (tid == 128) mbar_arrive(bars + 240);
        if (warp == 0) halo();
        TSTAMP1(8);
#pragma unroll
        for (int h = 0; h < 4; h++) {
            const int jb = 5 * (h >> 1) + 3 * (h & 1), js = 5 * (h >> 1) + 2;
#pragma unroll
            for (int e = 0; e < 4; e++) sc[h][0][e] = 0.f;
            mma_bf16(sc[h][0], f[0][jb], f[1][jb], f[0][jb + 1], f[1][jb + 1], kp[jb], kp[jb + 1]);
            mma_bf16_k8(sc[h][0], qs[h][0], qs[h][1], kp[js]);
        }
        if (warp > 4) { __syncwarp(); if (lane == 0) mbar_arrive(bars + 240); }
        TSTAMP1T(3, 64);
        float p[4][4], sum[4][2];
        uint32_t lg[4][2], mx[4];
        const float rl[4] = {rk[0] * ra, rk[1] * ra, rk[2] * rb, rk[3] * rb};
        auto max2 = [](uint32_t a, uint32_t b) { uint32_t r; asm("max.bf16x2 %0, %1, %2;" : "=r"(r) : "r"(a), "r"(b)); return r; };
#pragma unroll
        for (int h = 0; h < 4; h++) {
            lg[h][0] = pack2((up0 ? sc[h][0][0] : sc[h][1][0]) * rl[0], (up0 ? sc[h][1][2] : sc[h][2][2]) * rl[2]);
            lg[h][1] = pack2((up1 ? sc[h][0][1] : sc[h][1][1]) * rl[1], (up1 ? sc[h][1][3] : sc[h][2][3]) * rl[3]);
            if (edge) {
                if (up0) lg[h][0] = __byte_perm(lg[h][0], 0xce6eu, 0x3254);
                if (up1) lg[h][1] = __byte_perm(lg[h][1], 0xce6eu, 0x3254);
            }
            mx[h] = max2(lg[h][0], lg[h][1]);
        }
#pragma unroll
        for (int o = 1; o <= 2; o <<= 1)
#pragma unroll
            for (int h = 0; h < 4; h++) mx[h] = max2(mx[h], __shfl_xor_sync(~0u, mx[h], o));
#pragma unroll
        for (int h = 0; h < 4; h++)
#pragma unroll
            for (int r = 0; r < 2; r++) {
                const float m = __uint_as_float(r ? mx[h] & 0xffff0000u : mx[h] << 16);
#pragma unroll
                for (int e = 0; e < 2; e++)
                    asm("ex2.approx.ftz.f32 %0, %1;" : "=f"(p[h][2 * r + e]) : "f"((__uint_as_float(r ? lg[h][e] & 0xffff0000u : lg[h][e] << 16) - m) * 1.4426950408889634f));
                sum[h][r] = p[h][2 * r] + p[h][2 * r + 1];
            }
#pragma unroll
        for (int o = 1; o <= 2; o <<= 1)
#pragma unroll
            for (int h = 0; h < 4; h++)
#pragma unroll
                for (int r = 0; r < 2; r++) sum[h][r] += __shfl_xor_sync(~0u, sum[h][r], o);
        TSTAMP1T(5, 64);
        const uint32_t mu = (up0 ? 0xffffu : 0u) | (up1 ? 0xffff0000u : 0u);
        uint32_t ob[10][2];
#pragma unroll
        for (int P = 0; P < 2; P++) {
            float os[2][4];
#pragma unroll
            for (int e = 0; e < 2; e++) {
                const int h = 2 * P + e;
                const float i0 = rcp_apx(sum[h][0]), i1 = rcp_apx(sum[h][1]);
                const uint32_t w0 = pack2(p[h][0] * rk[0] * i0, p[h][1] * rk[1] * i0), w1 = pack2(p[h][2] * rk[2] * i1, p[h][3] * rk[3] * i1);
#pragma unroll
                for (int dt = 0; dt < 3; dt++) {
                    const int j = 5 * P + (dt < 2 ? 3 * e + dt : 2);
                    float o[4] = {0.f, 0.f, 0.f, 0.f};
                    mma_bf16(o, w0 & ~mu, w1 & mu, 0u, w1 & ~mu, vb[j][0], vb[j][1]);
                    mma_bf16_k8(o, w0 & mu, 0u, vp[j]);
                    if (dt < 2) { ob[j][0] = pack2(o[0], o[1]); ob[j][1] = pack2(o[2], o[3]); }
                    else { os[e][0] = o[0]; os[e][1] = o[1]; os[e][2] = o[2]; os[e][3] = o[3]; }
                }
            }
#pragma unroll
            for (int k = 0; k < 4; k++) os[0][k] = t < 2 ? os[0][k] : os[1][k];
            ob[5 * P + 2][0] = pack2(os[0][0], os[0][1]); ob[5 * P + 2][1] = pack2(os[0][2], os[0][3]);
        }
        const uint32_t sl = sbase + (wg ? A1_SM_A1 : A1_SM_A0);
        const uint32_t o0 = (warp & 3) * 2048 + g * 64 + ((t ^ (g >> 1)) << 4), o1 = 8192 + (warp & 3) * 512 + g * 32 + ((t ^ ((g >> 2) << 1)) << 3);
        mbar_wait(bar_done, 0);
        if (wg == 0) mbar_wait(bar_kvf, 0);
#pragma unroll
        for (int h = 0; h < 2; h++) {
            asm volatile("st.shared.v4.u32 [%0], {%1,%2,%3,%4};" ::"r"(sl + o0 + h * 1024), "r"(ob[0][h]), "r"(ob[1][h]), "r"(ob[2][h]), "r"(ob[3][h]) : "memory");
            asm volatile("st.shared.v4.u32 [%0], {%1,%2,%3,%4};" ::"r"(sl + o0 + h * 1024 + 512), "r"(ob[4][h]), "r"(ob[5][h]), "r"(ob[6][h]), "r"(ob[7][h]) : "memory");
            asm volatile("st.shared.v2.u32 [%0], {%1,%2};" ::"r"(sl + o1 + h * 256), "r"(ob[8][h]), "r"(ob[9][h]) : "memory");
        }
        fence_async_smem();
        __syncwarp();
        TSTAMP1T(4, 64);
        TSTAMP1(1);
        TSTAMP2(1);
        const unsigned char* ot = reinterpret_cast<const unsigned char*>(of) + mb * 163840 + wg * 10240;
        if (lane == 0) {
            asm volatile("cp.async.bulk.global.shared::cta.bulk_group [%0], [%1], 2048;" ::"l"(ot + hg * 20480 + (warp & 3) * 2048), "r"(sl + (warp & 3) * 2048) : "memory");
            asm volatile("cp.async.bulk.global.shared::cta.bulk_group [%0], [%1], 512;" ::"l"(ot + hg * 20480 + 8192 + (warp & 3) * 512), "r"(sl + 8192 + (warp & 3) * 512) : "memory");
            asm volatile("cp.async.bulk.commit_group;" ::: "memory");
            if (wg == 0) mbar_arrive(bar_pv);
            asm volatile("cp.async.bulk.wait_group 0;" ::: "memory");
            asm volatile(A1_FRED " [%0], 1;" ::"l"(reinterpret_cast<uint32_t*>(rsum + 2 * SEQ) + (((layer * 16 + mb) * 2 + wg) * 8 + hg) * FSTR) : "memory");
            DBGC(4 + warp);
        }
        TSTAMP4(11);
        float ac2[40];
        const uint64_t db0 = make_desc(sbase, 128, 1280, 0), da0 = make_desc(sl, 16, 1024, 2), da1 = make_desc(sl + 8192, 16, 256, 3);
        const uint32_t o7 = wg ? 640 : (A1_SM_W0 - A1_SM_A0) >> 4;
        const uint32_t trow = ((lane & 7) + 8 * (lane >> 4)) * 128 + (((2 * (warp & 3) + ((lane >> 3) & 1)) ^ (lane & 7)) << 4);
        uint32_t xr[10][2];
        mbar_wait(bar_f2 + 64 * wg + 64, 0);
        if (layer == 0) {
#pragma unroll
            for (int j = 0; j < 10; j += 2) ldsm_x4(&xr[j][0], sl + 51200 + (16 * (warp & 3) + (lane & 15)) * 160 + (lane >> 4) * 16 + 16 * j);
        } else {
#pragma unroll
            for (int j = 0; j < 10; j += 2) ldsm_x4_t(&xr[j][0], sl + 51200 + trow + 1024 * j);
        }
        const uint32_t ri = __shfl_sync(~0u, layer * SEQ + (wg * 2 + ((g >> 1) & 1)) * 512 + (mb * 16 + 4 * (warp & 3) + (g >> 2)) * 2 + (g & 1), lane);
        mbar_wait(bar_wo, 0);
        if (wg) mbar_wait(bar_pv, 0);
        if (wg) asm volatile("bar.sync 2, 128;" ::: "memory"); else asm volatile("bar.sync 1, 128;" ::: "memory");
        TSTAMP2(2);
#pragma unroll
        for (int q = 0; q < 8; q++) {
            uint32_t bo = wo_off(0) >> 4;
            if (q) {
                mbar_wait(bar_f2 + 64 * wg + 8 * q, 0);
                asm volatile("ld.shared.u32 %0, [%1];" : "=r"(bo) : "r"(que + 32 * wg + 4 * q) : "memory");
                bo = __shfl_sync(~0u, bo, 0);
                TSTAMP4(q);
                if (q == 1 && (tid & 127) == 0) DBGC(29 + 8 * wg);
            }
            wgmma_fence();
#pragma unroll
            for (int j = 0; j < 5; j++) wgmma_n80(ac2, (j < 4 ? da0 : da1) + (q == 7 ? o7 : 0u) + (uint64_t)((q < 6 ? q * 640 : 0) + (j & 2) * 16 + (j & 1) * 2), db0 + bo + (uint64_t)(16 * j), j || q);
            wgmma_commit();
            if (q == 0) {
                wgmma_wait<0>();
                if ((tid & 127) == 0) { mbar_arrive(bar_e2 + 16 * wg); mbar_arrive(bar_e2 + 8); }
            }
            if (q == 2 && wg) {
                wgmma_wait<1>();
                if (tid == 128) mbar_arrive(bar_e2 + 24);
            }
        }
        if ((tid & 127) == 0) DBGC(28 + wg * 8 + 7);
        TSTAMP2(3);
        wgmma_wait<0>();
        TSTAMP2(4);
        if (__any_sync(~0u, ac2[0] != ac2[0] || ac2[2] != ac2[2])) {
#pragma unroll
            for (int i = 0; i < 40; i++) ac2[i] = 0.f;
#pragma unroll 1
            for (int st = 0; st < 40; st++) {
                const int h = st / 5, u = st - 5 * h;
                const unsigned char* ap = ot + h * 20480 + (u < 4 ? o0 + (u >> 1) * 512 + (u & 1) * 8 : o1);
                uint32_t a[4];
#pragma unroll 1
                for (int it = 0; it < SPIN_MAX; it++) {
                    asm volatile("ld.relaxed.gpu.global.v2.u32 {%0,%1}, [%2];" : "=r"(a[0]), "=r"(a[2]) : "l"(ap) : "memory");
                    asm volatile("ld.relaxed.gpu.global.v2.u32 {%0,%1}, [%2];" : "=r"(a[1]), "=r"(a[3]) : "l"(ap + (u < 4 ? 1024 : 256)) : "memory");
                    if (a[0] != ~0u && a[1] != ~0u && a[2] != ~0u && a[3] != ~0u) break;
                }
                __syncwarp();
                const unsigned char* bp = wo + (hg * 8 + (h == hg ? 0 : h + (h < hg))) * WOB + g * 16 + (u < 4 ? ((u >> 1) * 4 + t) * 128 + (u & 1) * 8 : (8 + (t >> 1)) * 128 + (t & 1) * 8);
#pragma unroll
                for (int n = 0; n < 10; n++) {
                    const uint2 b = __ldcg(reinterpret_cast<const uint2*>(bp + 1280 * n));
                    mma_bf16(ac2 + 4 * n, a[0], a[1], a[2], a[3], b.x, b.y);
                }
            }
        }
#pragma unroll
        for (int j = 0; j < 10; j++)
#pragma unroll
            for (int hh = 0; hh < 2; hh++) {
                const uint32_t a = pack2(ac2[4 * j + 2 * hh], ac2[4 * j + 2 * hh + 1]);
                const __nv_bfloat162 r = __hadd2_rn(*reinterpret_cast<const __nv_bfloat162*>(&xr[j][hh]), *reinterpret_cast<const __nv_bfloat162*>(&a));
                xr[j][hh] = *reinterpret_cast<const uint32_t*>(&r);
            }
        const uint32_t so = sl + 30720;
#pragma unroll
        for (int j = 0; j < 10; j += 2) stsm_x4_t(so + trow + 1024 * j, xr[j][0], xr[j][1], xr[j + 1][0], xr[j + 1][1]);
        fence_async_smem();
        if (wg) asm volatile("bar.sync 2, 128;" ::: "memory"); else asm volatile("bar.sync 1, 128;" ::: "memory");
        TSTAMP2(5);
        if ((tid & 127) == 0) {
            asm volatile("cp.async.bulk.tensor.2d.global.shared::cta.bulk_group [%0, {%1, %2}], [%3];" ::"l"(&tmX1), "r"(mb * 128 + 64 * wg), "r"(hg * 80), "r"(so) : "memory");
            asm volatile("cp.async.bulk.commit_group;" ::: "memory");
        }
        __syncwarp();
        const float p0 = *(volatile const float*)&rw[g].x, p1 = *(volatile const float*)&rw[g + 8].x;
        float s[3][4] = {};
        const uint32_t pp[2] = {__byte_perm(__float_as_uint(p0), 0, 0x3232), __byte_perm(__float_as_uint(p1), 0, 0x3232)};
#pragma unroll
        for (int j = 0; j < 10; j += 2) {
            const uint32_t d0 = sub2(xr[j][0], pp[0]), d1 = sub2(xr[j][1], pp[1]), d2 = sub2(xr[j + 1][0], pp[0]), d3 = sub2(xr[j + 1][1], pp[1]);
            mma_bf16(s[0], xr[j][0], xr[j][1], xr[j + 1][0], xr[j + 1][1], 0x3f803f80u, 0x3f803f80u);
            mma_bf16(s[1], d0, d1, d2, d3, d0, d2);
            mma_bf16(s[2], d0, d1, d2, d3, d1, d3);
        }
        if (t == (g >> 1)) {
            float2* rp = rsum + ri;
            asm volatile("red.relaxed.gpu.global.add.v2.f32 [%0], {%1, %2};" ::"l"(rp), "f"(fmaf(-80.f, p0, s[0][0])), "f"((g & 1) ? s[1][1] : s[1][0]) : "memory");
            asm volatile("red.relaxed.gpu.global.add.v2.f32 [%0], {%1, %2};" ::"l"(rp + 4), "f"(fmaf(-80.f, p1, s[0][2])), "f"((g & 1) ? s[2][3] : s[2][2]) : "memory");
        }
        asm volatile("cp.async.bulk.wait_group.read 0;" ::: "memory");
        TSTAMP2(6);
        if (tid == 0) DBGC(63);
        if (tid == 128) DBGC(28);
        if (tid == 0) DBGCAL(2);
        GSTAMP(g_tim1, 14);
        SPAN(1 + 4 * layer, 3);
    }
}

static int h_nsm;
static void* h_sym[11];
static TileTab h_tab;
static CUtensorMap h_tmX0, h_tmX1, h_tmR0, h_tmR1, h_tmX1st, h_tmOut, h_tmWq, h_tmWo;
typedef CUresult (*PFN_encodeTiled)(CUtensorMap*, CUtensorMapDataType, cuuint32_t, void*, const cuuint64_t*, const cuuint64_t*,
                                    const cuuint32_t*, const cuuint32_t*, CUtensorMapInterleave, CUtensorMapSwizzle,
                                    CUtensorMapL2promotion, CUtensorMapFloatOOBfill);
static void make_tmap(CUtensorMap* tm, const void* ptr, uint64_t cols, uint64_t rows, uint32_t bc, uint32_t br, CUtensorMapSwizzle sw, uint64_t pitch = 0, uint64_t hi = 0, uint32_t bh = 2) {
    static PFN_encodeTiled fn = nullptr;
    if (!fn) {
        void* p = nullptr; cudaDriverEntryPointQueryResult qr;
        cudaGetDriverEntryPoint("cuTensorMapEncodeTiled", &p, cudaEnableDefault, &qr);
        fn = (PFN_encodeTiled)p;
    }
    if (br == 0) {
        cuuint64_t dims[4] = {cols, 2, rows / 8, 4}; cuuint64_t strides[3] = {cols * 2, cols * 16, cols * 4};
        cuuint32_t box[4] = {bc, 2, 8, 4}; cuuint32_t es[4] = {1, 1, 1, 1};
        fn(tm, CU_TENSOR_MAP_DATA_TYPE_BFLOAT16, 4, const_cast<void*>(ptr), dims, strides, box, es, CU_TENSOR_MAP_INTERLEAVE_NONE, sw,
           CU_TENSOR_MAP_L2_PROMOTION_L2_128B, CU_TENSOR_MAP_FLOAT_OOB_FILL_NONE);
        return;
    }
    if (bh == 5) {
        cuuint64_t dims[5] = {64, 64, 2, 16, 10}; cuuint64_t strides[4] = {pitch * 2, hi * 2, cols * 2, rows * 2};
        cuuint32_t box[5] = {64, 64, 2, 1, 1}; cuuint32_t es[5] = {1, 1, 1, 1, 1};
        fn(tm, CU_TENSOR_MAP_DATA_TYPE_BFLOAT16, 5, const_cast<void*>(ptr), dims, strides, box, es, CU_TENSOR_MAP_INTERLEAVE_NONE, sw,
           CU_TENSOR_MAP_L2_PROMOTION_L2_128B, CU_TENSOR_MAP_FLOAT_OOB_FILL_NONE);
        return;
    }
    if (hi) {
        cuuint64_t dims[3] = {cols, rows, hi == 64 ? 32u : 2u}; cuuint64_t strides[2] = {pitch * 2, hi * 2};
        cuuint32_t box[3] = {bc, br, bh}; cuuint32_t es[3] = {1, 1, 1};
        fn(tm, CU_TENSOR_MAP_DATA_TYPE_BFLOAT16, 3, const_cast<void*>(ptr), dims, strides, box, es, CU_TENSOR_MAP_INTERLEAVE_NONE, sw,
           CU_TENSOR_MAP_L2_PROMOTION_L2_128B, CU_TENSOR_MAP_FLOAT_OOB_FILL_NONE);
        return;
    }
    cuuint64_t dims[2] = {cols, rows}; cuuint64_t strides[1] = {(pitch ? pitch : cols) * 2};
    cuuint32_t box[2] = {bc, br}; cuuint32_t es[2] = {1, 1};
    fn(tm, CU_TENSOR_MAP_DATA_TYPE_BFLOAT16, 2, const_cast<void*>(ptr), dims, strides, box, es, CU_TENSOR_MAP_INTERLEAVE_NONE, sw,
       CU_TENSOR_MAP_L2_PROMOTION_L2_128B, CU_TENSOR_MAP_FLOAT_OOB_FILL_NONE);
}
template <typename... Args>
static void launch_pdl(void (*kern)(Args...), int grid, int block, int smem, Args... args) {
    cudaLaunchConfig_t cfg = {};
    cfg.gridDim = dim3(grid); cfg.blockDim = dim3(block); cfg.dynamicSmemBytes = smem; cfg.stream = cudaStreamPerThread;
    cudaLaunchAttribute at[1];
    at[0].id = cudaLaunchAttributeProgrammaticStreamSerialization; at[0].val.programmaticStreamSerializationAllowed = 1;
    cfg.attrs = at; cfg.numAttrs = 1;
    cudaLaunchKernelEx(&cfg, kern, args...);
}
static void launch_stage(int k, void* const* d_in, void* d_out) {
    const KgIn kg = {(const bf16*)d_in[4], (const bf16*)d_in[5], (const bf16*)d_in[6], (const bf16*)d_in[7], (const bf16*)d_in[8], (const bf16*)d_in[0], (const bf16*)d_in[1], (const bf16*)d_in[2],
                      (uint4*)h_sym[0], (uint4*)h_sym[1], (uint4*)h_sym[2], (uint4*)h_sym[3], (uint4*)h_sym[4], (float*)h_sym[5]};
    switch (k) {
        case 0: kgen_kernel<<<DM, KG_THREADS, 0, cudaStreamPerThread>>>(kg, h_tmWq, h_tmWo); break;
        case 1: launch_pdl(a1_kernel, h_nsm, A1_THREADS, A1_SMEM, 0, (const bf16*)d_in[0], (const unsigned char*)h_sym[1], (const unsigned char*)h_sym[2], (float2*)h_sym[4], (uint4*)h_sym[6], h_tmX0, h_tmR0, h_tmX1st, h_tab); break;
        case 3: launch_pdl(conv_kernel, DM / CV_CPB, CV_THREADS, CV_SMEM, (const bf16*)d_in[9], 0, (const uint4*)h_sym[7], (const float4*)h_sym[4], (const bf16*)h_sym[8], (bf16*)h_sym[9], (const uint4*)h_sym[0], (bf16*)h_sym[10], h_tmOut); break;
        case 5: launch_pdl(a1_kernel, h_nsm, A1_THREADS, A1_SMEM, 1, (const bf16*)d_in[0], (const unsigned char*)h_sym[1], (const unsigned char*)h_sym[2], (float2*)h_sym[4], (uint4*)h_sym[6], h_tmX1, h_tmR1, h_tmX1st, h_tab); break;
        case 7: launch_pdl(conv_kernel, DM / CV_CPB, CV_THREADS, CV_SMEM, (const bf16*)d_in[9], 1, (const uint4*)h_sym[7] + SEQ / 8, (const float4*)h_sym[4] + SEQ / 2, (const bf16*)h_sym[8], (bf16*)h_sym[10], (const uint4*)h_sym[0], (bf16*)h_sym[10], h_tmOut); break;
        default: break;
    }
}
static int n_stage_kernels() { return 9; }
static const char* stage_name(int k) { const char* n[] = {"kgen", "a1", "a2", "conv", "tr", "a1", "a2", "conv", "tr"}; return n[k]; }

extern "C" void kernel_launch(void* const* d_in, const int* in_sizes, int n_in, void* d_out, int out_size) {
    (void)in_sizes; (void)n_in; (void)out_size;
    static const void *p_in = nullptr, *p_w1 = nullptr, *p_w2 = nullptr, *p_out = nullptr;
    if (p_in != d_in[0] || p_w1 != d_in[1] || p_w2 != d_in[2] || p_out != d_out) {
        cudaFuncSetAttribute(conv_kernel, cudaFuncAttributeMaxDynamicSharedMemorySize, CV_SMEM);
        cudaFuncSetAttribute(kgen_kernel, cudaFuncAttributePreferredSharedMemoryCarveout, 100);
        cudaFuncSetAttribute(a1_kernel, cudaFuncAttributeMaxDynamicSharedMemorySize, A1_SMEM);
        int dev; cudaGetDevice(&dev); cudaDeviceGetAttribute(&h_nsm, cudaDevAttrMultiProcessorCount, dev);
        if (h_nsm != 132) h_nsm = 128;
        h_tab.ns = h_nsm == 132 ? 132 : ~0u;
        for (int i = 0; i < 264; i++) {
            const int h = (i - 64) >> 1;
            const int t = i >= 132 ? i - 132 : i < 64 ? ((i >> 1) & 7) * 16 + (i >> 4) * 2 + (i & 1) : i < 120 ? (1 + h % 7) * 16 + 8 + (h / 7) * 2 + (i & 1) : i < 124 ? 128 : i - 116;
            const int hg = (4 * (t >> 6) + (t & 3)) & 7;
            h_tab.e[i] = {(unsigned char)((t >> 2) & 15), (unsigned char)hg, (unsigned char)(5 * (hg >> 2)), (unsigned char)t, (uint32_t)(hg * 10 * WQ_STAGE)};
        }
        cudaGetSymbolAddress(&h_sym[0], g_tap); cudaGetSymbolAddress(&h_sym[1], g_wq); cudaGetSymbolAddress(&h_sym[2], g_wo);
        cudaGetSymbolAddress(&h_sym[3], g_halo); cudaGetSymbolAddress(&h_sym[4], g_sum); cudaGetSymbolAddress(&h_sym[5], g_csp); cudaGetSymbolAddress(&h_sym[6], g_of);
        cudaGetSymbolAddress(&h_sym[7], g_piv); cudaGetSymbolAddress(&h_sym[8], g_x1T); cudaGetSymbolAddress(&h_sym[9], g_xcT); cudaGetSymbolAddress(&h_sym[10], g_yT);
        void *px1, *px2;
        cudaGetSymbolAddress(&px1, g_x1T); cudaGetSymbolAddress(&px2, g_xcT);
        make_tmap(&h_tmX0, d_in[0], 128 * 640, 64, 64, 64, CU_TENSOR_MAP_SWIZZLE_128B, 1280, 640, 5);
        make_tmap(&h_tmX1, px2, 128, 64 * XCP, 64, 64, CU_TENSOR_MAP_SWIZZLE_128B, XCP, 64, 5);
        make_tmap(&h_tmR0, d_in[0], 640, 1024, 80, 64, CU_TENSOR_MAP_SWIZZLE_NONE, 1280, 640, 1);
        make_tmap(&h_tmR1, px2, 64, 640, 64, 80, CU_TENSOR_MAP_SWIZZLE_128B, XCP, 64, 1);
        make_tmap(&h_tmX1st, px1, 2048, 640, 64, 80, CU_TENSOR_MAP_SWIZZLE_128B, XCP);
        make_tmap(&h_tmWq, d_in[1], 1920, 640, 32, 0, CU_TENSOR_MAP_SWIZZLE_64B);
        make_tmap(&h_tmWo, d_in[2], 640, 640, 32, 80, CU_TENSOR_MAP_SWIZZLE_64B);
        make_tmap(&h_tmOut, d_out, 640, 2048, 80, 8, CU_TENSOR_MAP_SWIZZLE_NONE);
        p_in = d_in[0]; p_w1 = d_in[1]; p_w2 = d_in[2]; p_out = d_out;
    }
    for (int k = 0; k < n_stage_kernels(); k++) launch_stage(k, d_in, d_out);
}
```

```cpp
#include <cuda_runtime.h>
#include <cuda_bf16.h>
#include <stdint.h>
#include <cuda.h>

typedef __nv_bfloat16 bf16;

constexpr int SEQ = 2048;
constexpr int DM = 640;
constexpr int NMODE = 192;

__device__ __forceinline__ float bf2f(bf16 v) { return __bfloat162float(v); }
__device__ __forceinline__ float rbf(float v) {
    uint32_t r;
    asm("cvt.rn.bf16x2.f32 %0, %1, %2;" : "=r"(r) : "f"(v), "f"(0.f));
    return __uint_as_float(r);
}
__device__ __forceinline__ uint32_t pack2(float lo, float hi) {
    __nv_bfloat162 t = __floats2bfloat162_rn(lo, hi);
    return *reinterpret_cast<uint32_t*>(&t);
}
__device__ __forceinline__ void pdl_sync() {
    asm volatile("griddepcontrol.wait;" ::: "memory");
    asm volatile("griddepcontrol.launch_dependents;" ::: "memory");
}
__device__ __forceinline__ float sqrt_apx(float v) { float r; asm("sqrt.approx.ftz.f32 %0, %1;" : "=f"(r) : "f"(v)); return r; }
__device__ __forceinline__ float rcp_apx(float v) { float r; asm("rcp.approx.ftz.f32 %0, %1;" : "=f"(r) : "f"(v)); return r; }
__device__ __forceinline__ uint32_t smem_u32(const void* p) { return (uint32_t)__cvta_generic_to_shared(p); }

constexpr int TPAD = 16;
constexpr int DLEN = 544;
constexpr int TAP_W2 = DLEN * 8, TAP_W3 = TAP_W2 + 768, TAP_C = TAP_W3 + 768, TAPB = TAP_C + 384;
__device__ __align__(128) uint4 g_tap[DM * 128];
#define XPAD 64
constexpr int XCP = SEQ + XPAD;
__device__ __align__(128) bf16 g_x1T[DM * XCP];
__device__ __align__(128) bf16 g_xcT[DM * XCP];
__device__ __align__(128) uint4 g_of[128 * 1280];
constexpr int WQ_STAGE = 240 * 128, WOB = 80 * 160;
__device__ __align__(128) uint4 g_wq[8 * 10 * WQ_STAGE / 16];
__device__ __align__(128) uint4 g_wo[64 * WOB / 16];
__device__ __align__(16) float g_csp[10 * 1920];
#define FSTR 32
__device__ __align__(128) float2 g_sum[2 * SEQ + 256 * FSTR];
__device__ __align__(16) bf16 g_piv[2 * SEQ];
__device__ __align__(128) bf16 g_yT[DM * XCP];
__device__ uint32_t g_epoch;
__device__ __align__(16) unsigned long long g_rstat[SEQ];
__device__ __align__(128) uint4 g_halo[640 * 148];
__device__ __forceinline__ unsigned long long tagw(uint32_t payload, uint32_t tag) { return ((unsigned long long)tag << 32) | payload; }
__device__ __forceinline__ ulonglong2 ld_tag2(const ulonglong2* p) {
    ulonglong2 v;
    asm volatile("ld.relaxed.gpu.global.v2.u64 {%0, %1}, [%2];" : "=l"(v.x), "=l"(v.y) : "l"(p) : "memory");
    return v;
}
__device__ __forceinline__ bool tag_ok(ulonglong2 v, uint32_t tag) { return (uint32_t)(v.x >> 32) == tag && (uint32_t)(v.y >> 32) == tag; }
__device__ __forceinline__ uint32_t ld_epoch() { uint32_t v; asm volatile("ld.relaxed.gpu.global.u32 %0, [%1];" : "=r"(v) : "l"(&g_epoch) : "memory"); return v + 1; }
constexpr int SPIN_MAX = 1 << 20;
__device__ uint32_t g_started[4];
__device__ __forceinline__ void sm_started(int slot) { asm volatile("red.relaxed.gpu.global.add.u32 [%0], 1;" ::"l"(g_started + slot) : "memory"); }
__device__ __noinline__ void sm_idle(int slot) {
    if (threadIdx.x) return;
    sm_started(slot);
    const uint32_t want = ld_epoch() * gridDim.x;
    pdl_sync();
#pragma unroll 1
    for (int it = 0; it < SPIN_MAX; it++) {
        uint32_t v;
        asm volatile("ld.relaxed.gpu.global.u32 %0, [%1];" : "=r"(v) : "l"(g_started + slot) : "memory");
        if ((int)(v - want) >= 0) break;
        __nanosleep(100);
    }
}
struct TileTab { uint32_t ns, pad; struct { unsigned char mb, hg, kb0, tile; uint32_t woff; } __align__(8) e[264]; };
__device__ __forceinline__ bool elect() {
    uint32_t p;
    asm volatile("{\n.reg .pred p;\nelect.sync _|p, 0xffffffff;\nselp.b32 %0, 1, 0, p;\n}" : "=r"(p));
    return p;
}
#define DBG_SYMS
#define TSTAMP(i)
#define TSTAMP1(i)
#define TSTAMP1T(i, t)
#define TSTAMP1X(i, t)
#define SPAN(k, i)
#define GSTAMP(arr, i)
#define TSTAMP2(i)
#define TSTAMP3(i)
#define TSTAMP4(i)
#define TSTAMPK(i, t)
#define DBGC(i)
#define DBGV(i, v)
#define DBGCAL(i)

__device__ __forceinline__ void mma_bf16(float* d, uint32_t a0, uint32_t a1, uint32_t a2, uint32_t a3, uint32_t b0, uint32_t b1) {
    asm volatile("mma.sync.aligned.m16n8k16.row.col.f32.bf16.bf16.f32 {%0,%1,%2,%3}, {%4,%5,%6,%7}, {%8,%9}, {%0,%1,%2,%3};"
                 : "+f"(d[0]), "+f"(d[1]), "+f"(d[2]), "+f"(d[3]) : "r"(a0), "r"(a1), "r"(a2), "r"(a3), "r"(b0), "r"(b1));
}
__device__ __forceinline__ void mma_bf16_k8(float* d, uint32_t a0, uint32_t a1, uint32_t b0) {
    asm volatile("mma.sync.aligned.m16n8k8.row.col.f32.bf16.bf16.f32 {%0,%1,%2,%3}, {%4,%5}, {%6}, {%0,%1,%2,%3};"
                 : "+f"(d[0]), "+f"(d[1]), "+f"(d[2]), "+f"(d[3]) : "r"(a0), "r"(a1), "r"(b0));
}
__device__ __forceinline__ void ldsm_x4(uint32_t* r, uint32_t addr) {
    asm volatile("ldmatrix.sync.aligned.m8n8.x4.shared.b16 {%0,%1,%2,%3}, [%4];"
                 : "=r"(r[0]), "=r"(r[1]), "=r"(r[2]), "=r"(r[3]) : "r"(addr));
}

__device__ __forceinline__ void ldsm_x4_t(uint32_t* r, uint32_t addr) {
    asm volatile("ldmatrix.sync.aligned.m8n8.x4.trans.shared.b16 {%0,%1,%2,%3}, [%4];"
                 : "=r"(r[0]), "=r"(r[1]), "=r"(r[2]), "=r"(r[3]) : "r"(addr));
}
__device__ __forceinline__ void mbar_init(uint32_t bar, int count) { asm volatile("mbarrier.init.shared::cta.b64 [%0], %1;" ::"r"(bar), "r"(count)); }
__device__ __forceinline__ void mbar_arrive(uint32_t bar) { asm volatile("mbarrier.arrive.shared::cta.b64 _, [%0];" ::"r"(bar) : "memory"); }
__device__ __forceinline__ void mbar_wait(uint32_t bar, uint32_t parity) {
    asm volatile("{\n.reg .pred p;\nWAIT_LOOP:\n"
                 "mbarrier.try_wait.parity.shared::cta.b64 p, [%0], %1;\n"
                 "@p bra.uni WAIT_DONE;\nbra.uni WAIT_LOOP;\nWAIT_DONE:\n}" ::"r"(bar), "r"(parity) : "memory");
}

__device__ __forceinline__ void mbar_expect_tx(uint32_t bar, uint32_t bytes) {
    asm volatile("mbarrier.arrive.expect_tx.shared::cta.b64 _, [%0], %1;" ::"r"(bar), "r"(bytes) : "memory");
}
__device__ __forceinline__ void tma_load_2d(uint32_t dst, const void* tmap, int c0, int c1, uint32_t bar) {
    asm volatile("cp.async.bulk.tensor.2d.shared::cluster.global.mbarrier::complete_tx::bytes [%0], [%1, {%3, %4}], [%2];"
                 ::"r"(dst), "l"(tmap), "r"(bar), "r"(c0), "r"(c1) : "memory");
}
__device__ __forceinline__ void tma_load_3d(uint32_t dst, const void* tmap, int c0, int c1, int c2, uint32_t bar) {
    asm volatile("cp.async.bulk.tensor.3d.shared::cluster.global.mbarrier::complete_tx::bytes [%0], [%1, {%3, %4, %5}], [%2];"
                 ::"r"(dst), "l"(tmap), "r"(bar), "r"(c0), "r"(c1), "r"(c2) : "memory");
}
__device__ __forceinline__ void fence_async_smem() { asm volatile("fence.proxy.async.shared::cta;" ::: "memory"); }
__device__ __forceinline__ void bulk_load(uint32_t dst, const void* src, uint32_t bytes, uint32_t bar) {
    asm volatile("cp.async.bulk.shared::cluster.global.mbarrier::complete_tx::bytes [%0], [%1], %2, [%3];"
                 ::"r"(dst), "l"(src), "r"(bytes), "r"(bar) : "memory");
}
__device__ __forceinline__ void tma_store_2d(const void* tmap, int c0, int c1, uint32_t src) {
    asm volatile("cp.async.bulk.tensor.2d.global.shared::cta.bulk_group [%0, {%1, %2}], [%3];" ::"l"(tmap), "r"(c0), "r"(c1), "r"(src) : "memory");
    asm volatile("cp.async.bulk.commit_group;" ::: "memory");
    asm volatile("cp.async.bulk.wait_group.read 0;" ::: "memory");
}
__device__ __forceinline__ void stsm_x4(uint32_t addr, uint32_t r0, uint32_t r1, uint32_t r2, uint32_t r3) {
    asm volatile("stmatrix.sync.aligned.m8n8.x4.shared.b16 [%0], {%1,%2,%3,%4};" ::"r"(addr), "r"(r0), "r"(r1), "r"(r2), "r"(r3) : "memory");
}
__device__ __forceinline__ void stsm_x4_t(uint32_t addr, uint32_t r0, uint32_t r1, uint32_t r2, uint32_t r3) {
    asm volatile("stmatrix.sync.aligned.m8n8.x4.trans.shared.b16 [%0], {%1,%2,%3,%4};" ::"r"(addr), "r"(r0), "r"(r1), "r"(r2), "r"(r3) : "memory");
}
__device__ __forceinline__ void prefetch_tmap(const void* tmap) { asm volatile("prefetch.tensormap [%0];" ::"l"(tmap) : "memory"); }

__device__ __forceinline__ float2 cexp_at(float wr2, float wi, float p) {
    float er;
    asm("ex2.approx.ftz.f32 %0, %1;" : "=f"(er) : "f"(wr2 * p));
    float th = wi * p;
    const float k = rintf(th * 0.15915494309189535f);
    th = fmaf(k, -6.2831854820251465f, th);
    th = fmaf(k, 1.7484555314695172e-7f, th);
    return make_float2(er * __cosf(th), er * __sinf(th));
}
__device__ __forceinline__ float2 cmul(float2 a, float2 b) {
    return make_float2(fmaf(a.x, b.x, -a.y * b.y), fmaf(a.x, b.y, a.y * b.x));
}
__device__ __forceinline__ float2 csqr(float2 a) { return make_float2(fmaf(a.x, a.x, -a.y * a.y), (a.x + a.x) * a.y); }
__device__ __forceinline__ uint32_t packh(float2 v) {
    uint32_t r;
    asm("cvt.rn.f16x2.f32 %0, %1, %2;" : "=r"(r) : "f"(v.y), "f"(v.x));
    return r;
}
__device__ __forceinline__ void mma_f16(float* d, uint32_t a0, uint32_t a1, uint32_t a2, uint32_t a3, uint32_t b0, uint32_t b1) {
    asm volatile("mma.sync.aligned.m16n8k16.row.col.f32.f16.f16.f32 {%0,%1,%2,%3}, {%4,%5,%6,%7}, {%8,%9}, {%0,%1,%2,%3};"
                 : "+f"(d[0]), "+f"(d[1]), "+f"(d[2]), "+f"(d[3]) : "r"(a0), "r"(a1), "r"(a2), "r"(a3), "r"(b0), "r"(b1));
}

struct KgIn { const bf16 *logA, *Aim, *Cre, *Cim, *logdt, *x, *wqkv, *wo; uint4 *tap, *wq, *wop, *halo, *sum; float* csp; };
constexpr int KG_THREADS = NMODE / 2;

__global__ void __launch_bounds__(KG_THREADS, 5) kgen_kernel(const KgIn in, const __grid_constant__ CUtensorMap tmWq, const __grid_constant__ CUtensorMap tmWo) {
    __shared__ __align__(8) unsigned long long wbar[3];
    __shared__ __align__(1024) uint4 tab[3 * 896];
    const int d = blockIdx.x, tid = threadIdx.x, lane = tid & 31, warp = __shfl_sync(~0u, tid >> 5, 0);
    SPAN(0, 0); SPAN(0, 1);
    TSTAMPK(0, 0);
    asm volatile("griddepcontrol.launch_dependents;" ::: "memory");
    const bf16 pdt = in.logdt[d];
    const uint32_t pla = reinterpret_cast<const uint32_t*>(in.logA)[d * KG_THREADS + tid], pai = reinterpret_cast<const uint32_t*>(in.Aim)[d * KG_THREADS + tid];
    const uint32_t pcr = reinterpret_cast<const uint32_t*>(in.Cre)[d * KG_THREADS + tid], pci = reinterpret_cast<const uint32_t*>(in.Cim)[d * KG_THREADS + tid];
    const bf16* pfq = tid < 30 ? in.wqkv + (size_t)(d * 30 + tid) * 64 : tid < 40 ? in.wo + (size_t)(d * 10 + tid - 30) * 64 : in.x + (size_t)(d * 32 + tid - 40) * 64;
    if (tid < 72) asm volatile("prefetch.global.L2 [%0];" ::"l"(pfq));
    asm volatile("st.global.v4.u32 [%0], {%1,%1,%1,%1};" ::"l"(in.halo + d * 148 + tid), "r"(~0u));
    if (tid < 52) asm volatile("st.global.v4.u32 [%0], {%1,%1,%1,%1};" ::"l"(in.halo + d * 148 + 96 + tid), "r"(~0u));
    const uint32_t tw = smem_u32(tab) + warp * 14336;
    if (lane == 0) { mbar_init(smem_u32(wbar + warp), 1); prefetch_tmap(d >= 200 ? &tmWo : &tmWq); }
    const int g = lane >> 2, t = lane & 3;
    const uint32_t sta = tw + lane * 128 + ((2 * (lane & 3) + ((lane >> 2) & 1)) << 4);
    const uint32_t lda = tw + t * 128 + ((g ^ (2 * t)) << 4);
    const uint32_t stb = tw + 12288 + lane * 64 + ((4 * ((lane >> 1) & 1) + ((lane >> 2) & 3)) << 3);
    const uint32_t ldb = tw + 12288 + t * 64 + ((g ^ (4 * (t >> 1))) << 3);
    auto sts4 = [&](int e, int off, uint32_t a, uint32_t b, uint32_t c, uint32_t dd) {
        asm volatile("st.shared.v4.u32 [%0], {%1,%2,%3,%4};" ::"r"((sta ^ (e << 4)) + off), "r"(a), "r"(b), "r"(c), "r"(dd) : "memory");
    };
    auto lds4 = [&](int sp, int off, uint32_t* r) {
        asm volatile("ld.shared.v4.u32 {%0,%1,%2,%3}, [%4];" : "=r"(r[0]), "=r"(r[1]), "=r"(r[2]), "=r"(r[3]) : "r"((lda ^ ((sp & 1) << 4)) + sp * 512 + off) : "memory");
    };
    const float dt = rbf(expf(bf2f(pdt)));
    float2 C[2], y1[2], z8[2], y128[2];
    float cmax = 0.f;
#pragma unroll
    for (int m = 0; m < 2; m++) {
        const float wr2 = -rbf(expf(__uint_as_float(m ? pla & 0xffff0000u : pla << 16))) * dt * 1.4426950408889634f;
        const float wi = __uint_as_float(m ? pai & 0xffff0000u : pai << 16) * dt;
        C[m] = make_float2(__uint_as_float(m ? pcr & 0xffff0000u : pcr << 16) * dt, -__uint_as_float(m ? pci & 0xffff0000u : pci << 16) * dt);
        cmax = fmaxf(cmax, fmaxf(fabsf(C[m].x), fabsf(C[m].y)));
        y1[m] = cexp_at(wr2, -wi, 1.f); z8[m] = cexp_at(wr2, wi, 8.f); y128[m] = cexp_at(wr2, -wi, 128.f);
    }
    const int ex = min(max((int)(__reduce_max_sync(~0u, __float_as_uint(cmax)) >> 23), 20), 240);
    const float scale = __uint_as_float((uint32_t)(127 + 10 + 127 - ex) << 23), unscale = 2.0f * __uint_as_float((uint32_t)(ex - 10) << 23);
    TSTAMPK(4, 0);
    float k2048 = 0.f;
    float acc[5][4];
#pragma unroll
    for (int j = 0; j < 5; j++)
#pragma unroll
        for (int k = 0; k < 4; k++) acc[j][k] = 0.f;
    uint32_t af[8][4];
    {
        float2 h0[2], h1[2], g0[2], g1[2], g2[2], g2b[2], g3[2], g4[2], y2[2], y4[2];
#pragma unroll
        for (int m = 0; m < 2; m++) {
            h0[m] = make_float2(1.f, 0.f); h1[m] = csqr(csqr(csqr(z8[m])));
            g0[m] = make_float2(C[m].x * scale, C[m].y * scale);
            g1[m] = cmul(g0[m], y128[m]);
            const float2 y256 = csqr(y128[m]), y512 = csqr(y256);
            g2b[m] = g2[m] = cmul(g0[m], y256); g3[m] = cmul(g0[m], y512); g4[m] = cmul(g3[m], y512);
            y2[m] = csqr(y1[m]); y4[m] = csqr(y2[m]);
            const float2 y1024 = csqr(y512);
            k2048 += fmaf(g4[m].x, y1024.x, -g4[m].y * y1024.y);
        }
#pragma unroll
        for (int e = 0; e < 8; e++) {
            sts4(e, 0, packh(h0[0]), packh(h1[0]), packh(h0[1]), packh(h1[1]));
            sts4(e, 4096, packh(g0[0]), packh(g0[1]), packh(g1[0]), packh(g1[1]));
#pragma unroll
            for (int m = 0; m < 2; m++)
                if (e < 7) { h0[m] = e ? cmul(h0[m], z8[m]) : z8[m]; h1[m] = cmul(h1[m], z8[m]); g0[m] = cmul(g0[m], y1[m]); g1[m] = cmul(g1[m], y1[m]); }
            if (e < 5) k2048 += __shfl_xor_sync(~0u, k2048, 1 << e);
        }
        __syncwarp();
#pragma unroll
        for (int e = 0; e < 8; e++) {
            uint32_t b[4];
            lds4(e, 0, af[e]); lds4(e, 4096, b);
            sts4(e, 8192, packh(g2[0]), packh(g2[1]), packh((e & 1) ? cmul(g3[0], y4[0]) : g3[0]), packh((e & 1) ? cmul(g3[1], y4[1]) : g3[1]));
            asm volatile("st.shared.v2.u32 [%0], {%1,%2};" ::"r"(stb ^ (e << 3)), "r"(packh(g4[0])), "r"(packh(g4[1])) : "memory");
#pragma unroll
            for (int m = 0; m < 2; m++)
                if (e < 7) {
                    g2[m] = e == 3 ? cmul(g2b[m], y128[m]) : cmul(g2[m], y2[m]);
                    if (e & 1) g3[m] = cmul(g3[m], y128[m]);
                    g4[m] = cmul(g4[m], y128[m]);
                }
            mma_f16(acc[0], af[e][0], af[e][1], af[e][2], af[e][3], b[0], b[1]);
            mma_f16(acc[1], af[e][0], af[e][1], af[e][2], af[e][3], b[2], b[3]);
        }
    }
    TSTAMPK(6, 0);
    const int job = d * 3 + warp;
    const bool isq = job < 600;
    const int scol = (isq ? job / 10 : (job - 600) >> 3) * 32, skb = isq ? job - (job / 10) * 10 : job & 7;
    fence_async_smem();
    __syncwarp();
    if (job < 760) {
        if (lane == 0) {
            mbar_expect_tx(smem_u32(wbar + warp), isq ? 4096 : 5120);
            if (isq) asm volatile("cp.async.bulk.tensor.4d.shared::cluster.global.mbarrier::complete_tx::bytes [%0], [%1, {%3, %4, %5, %4}], [%2];"
                                  ::"r"(tw + 4096), "l"(&tmWq), "r"(smem_u32(wbar + warp)), "r"(scol), "r"(0), "r"(skb * 8) : "memory");
            else tma_load_2d(tw + 3072, &tmWo, scol, skb * 80, smem_u32(wbar + warp));
        }
    } else if (job < 760 + 64) in.sum[(job - 760) * 32 + lane] = make_uint4(0, 0, 0, 0);
    else if (job < 760 + 80) reinterpret_cast<uint32_t*>(in.sum + 2048)[((job - 824) * 32 + lane) * FSTR] = 0;
#pragma unroll
    for (int sp = 0; sp < 8; sp++) {
        uint32_t c[4], e0, e1;
        lds4(sp, 8192, c);
        asm volatile("ld.shared.v2.u32 {%0,%1}, [%2];" : "=r"(e0), "=r"(e1) : "r"((ldb ^ ((sp & 3) << 3)) + sp * 256) : "memory");
        mma_f16(acc[2], af[sp][0], af[sp][1], af[sp][2], af[sp][3], c[0], c[1]);
        mma_f16(acc[3], af[sp][0], af[sp][1], af[sp][2], af[sp][3], c[2], c[3]);
        mma_f16(acc[4], af[sp][0], af[sp][1], af[sp][2], af[sp][3], e0, e1);
    }
    {
        float* Pp = reinterpret_cast<float*>(tab + warp * 896);
#pragma unroll
        for (int h = 0; h < 2; h++) {
            const int b = g + 8 * h;
            *reinterpret_cast<float2*>(Pp + 8 * b + 2 * t) = make_float2(acc[0][2 * h] * unscale, acc[0][2 * h + 1] * unscale);
            *reinterpret_cast<float2*>(Pp + 128 + 8 * b + 2 * t) = make_float2(acc[1][2 * h] * unscale, acc[1][2 * h + 1] * unscale);
            *reinterpret_cast<float2*>(Pp + 256 + 4 * b + 2 * (t & 1) + 64 * (t >> 1)) = make_float2(acc[2][2 * h] * unscale, acc[2][2 * h + 1] * unscale);
            *reinterpret_cast<float2*>(Pp + 384 + 2 * b + 32 * t) = make_float2(acc[3][2 * h] * unscale, acc[3][2 * h + 1] * unscale);
            Pp[512 + b + 32 * t] = acc[4][2 * h] * unscale;
            Pp[512 + b + 32 * t + 16] = acc[4][2 * h + 1] * unscale;
        }
        if (lane == 0) Pp[640] = k2048 * unscale;
    }
    TSTAMPK(7, 0);
    __syncthreads();
    TSTAMPK(9, 0);
    const float* Kp = reinterpret_cast<const float*>(tab);
    auto ksum = [&](int i) -> float { return (Kp[i] + Kp[3584 + i]) + Kp[7168 + i]; };
    auto ksum4 = [&](int q) -> float4 {
        const float4 a = reinterpret_cast<const float4*>(Kp)[q], b = reinterpret_cast<const float4*>(Kp)[896 + q], c = reinterpret_cast<const float4*>(Kp)[1792 + q];
        return make_float4((a.x + b.x) + c.x, (a.y + b.y) + c.y, (a.z + b.z) + c.z, (a.w + b.w) + c.w);
    };
    {
        uint2* E4 = reinterpret_cast<uint2*>(in.tap + d * 128);
        float4 v = ksum4(tid), u = ksum4(96 + min(tid, 64));
        const float cor = rbf(ksum(tid == 95 ? 384 : 512));
        if (tid == 95) v.w -= cor;
        if (tid == 31) u.w -= cor;
        const uint32_t lo = pack2(v.x, v.y), hi = pack2(v.z, v.w);
        if (tid < 64) {
            E4[6 + tid] = make_uint2(lo, hi);
            E4[(tid < 32 ? 159 : 209 - 32) + tid] = make_uint2(pack2(u.x, u.y), pack2(u.z, u.w));
        } else {
            const uint32_t nx = __shfl_down_sync(~0u, lo, 1);
            in.tap[d * 128 + 35 + tid - 64] = make_uint4(__byte_perm(lo, 0, 0x1010), __byte_perm(lo, hi, 0x5432), __byte_perm(hi, 0, 0x1010), __byte_perm(hi, tid == 95 ? 0u : nx, 0x5432));
            if (tid == 64) E4[241] = make_uint2(pack2(u.x, 0.f), 0u);
        }
    }
    TSTAMPK(10, 0);
    if (isq) {
        mbar_wait(smem_u32(wbar + warp), 0);
        const uint32_t src = tw + 4096 + ((lane >> 3) * 16 + (lane & 7)) * 64;
#pragma unroll
        for (int cg = 0; cg < 4; cg++) {
            const int col = scol + 8 * cg, sec = col / DM, r = col - sec * DM, hg = r / 80;
            const int n = hg * 160 + sec * 80 + r;
            unsigned char* dst = reinterpret_cast<unsigned char*>(in.wq) + (hg * 9 + (hg < 4 ? skb : skb < 5 ? skb + 5 : skb - 5)) * WQ_STAGE + (n + g) * 128;
            float cs[4] = {0.f, 0.f, 0.f, 0.f};
#pragma unroll
            for (int h = 0; h < 2; h++) {
                uint32_t w[4];
                ldsm_x4_t(w, src + h * 512 + ((cg ^ ((lane >> 1) & 3)) << 4));
                *reinterpret_cast<uint4*>(dst + (((4 * h + t) ^ g) << 4)) = make_uint4(w[0], w[1], w[2], w[3]);
                mma_bf16(cs, 0x3f803f80u, 0u, 0x3f803f80u, 0u, w[0], w[1]);
                mma_bf16(cs, 0x3f803f80u, 0u, 0x3f803f80u, 0u, w[2], w[3]);
            }
            if (g == cg) *reinterpret_cast<float2*>(in.csp + skb * 1920 + n + 2 * t) = make_float2(cs[0], cs[1]);
        }
    } else if (job < 760) {
        mbar_wait(smem_u32(wbar + warp), 0);
#pragma unroll 1
        for (int cg = 0; cg < 4; cg++) {
            const int col = scol + 8 * cg, hg = col / 80;
            unsigned char* dst = reinterpret_cast<unsigned char*>(in.wop) + (hg * 7 + (skb == hg ? 0 : skb + (skb < hg))) * WOB + col * 160 + g * 16;
            const int r0 = lane, r2 = 64 + (lane & 15);
            uint32_t w[12];
            ldsm_x4_t(w, tw + 3072 + r0 * 64 + ((cg ^ ((r0 >> 1) & 3)) << 4));
            ldsm_x4_t(w + 4, tw + 3072 + 2048 + r0 * 64 + ((cg ^ ((r0 >> 1) & 3)) << 4));
            ldsm_x4_t(w + 8, tw + 3072 + r2 * 64 + ((cg ^ ((r2 >> 1) & 3)) << 4));
            *reinterpret_cast<uint4*>(dst + t * 128) = make_uint4(w[0], w[1], w[2], w[3]);
            *reinterpret_cast<uint4*>(dst + 512 + t * 128) = make_uint4(w[4], w[5], w[6], w[7]);
            *reinterpret_cast<uint2*>(dst + 1024 + (t >> 1) * 128 + (t & 1) * 8) = make_uint2(w[8], w[9]);
        }
    }
    TSTAMPK(11, 0);
    SPAN(0, 3);
}

#define CV_MODE 0
#define CV_LD __ldcg
#define CV_LDX __ldcg
#define CV_SLEEP 100
constexpr int CV_CPB = 5;
constexpr int CV_THREADS = 512;
constexpr int UPADF = 128;
constexpr int ULEN = UPADF + SEQ + 80;
constexpr int XLEN = SEQ + 16;
constexpr int BX_5 = 0, BX_3 = 3264, BX_9 = 6528, BX_7 = 8960, BX_LEN = 11392;
constexpr int CV_SM_T = 0;
constexpr int CV_SM_B = CV_CPB * TAPB;
constexpr int CV_SM_U = CV_SM_B + CV_CPB * BX_LEN;
constexpr int CV_SM_X = CV_SM_U + CV_CPB * ULEN * 2;
constexpr int CV_SM_Y = CV_SM_X + CV_CPB * XLEN * 2;
constexpr int CV_SM_P = CV_SM_Y + CV_CPB * XLEN * 2;
constexpr int CV_SM_CNT = CV_SM_P + 6 * 4096;
constexpr int CV_SM_O = (CV_SM_CNT + 128 + 127) & ~127;
constexpr int CV_SMEM = CV_SM_O + 20480;
static_assert(CV_SM_B % 128 == 0 && CV_SM_CNT % 16 == 0, "layout");

__device__ __forceinline__ uint32_t sub2(uint32_t x, uint32_t m) {
    const __nv_bfloat162 d = __hsub2(*reinterpret_cast<const __nv_bfloat162*>(&x), *reinterpret_cast<const __nv_bfloat162*>(&m));
    return *reinterpret_cast<const uint32_t*>(&d);
}
__device__ __forceinline__ uint32_t add2(uint32_t x, uint32_t y) {
    const __nv_bfloat162 d = __hadd2_rn(*reinterpret_cast<const __nv_bfloat162*>(&x), *reinterpret_cast<const __nv_bfloat162*>(&y));
    return *reinterpret_cast<const uint32_t*>(&d);
}
__device__ __forceinline__ void cp_async16(uint32_t dst, const void* src) {
    asm volatile("cp.async.cg.shared.global [%0], [%1], 16;" ::"r"(dst), "l"(src));
}
__device__ __forceinline__ void cp_async_wait_all() { asm volatile("cp.async.wait_all;" ::: "memory"); }

template <bool FULL>
__device__ __forceinline__ void direct_pass(float (&acc)[8][4], uint32_t ub, uint32_t o0, uint32_t o1, const uint2* __restrict__ Tp, bool first_half) {
    uint32_t sw[8][8];
#pragma unroll
    for (int j = 0; j < 8; j++) { ldsm_x4(&sw[j][0], ub + o0 + j * 256); ldsm_x4(&sw[j][4], ub + o1 + j * 256); }
#pragma unroll
    for (int M = 0; M < 4; M++) {
#pragma unroll
        for (int i = 0; i < 4; i++) {
            const uint2 hi = Tp[128 * M + 16 * i], lo = Tp[128 * M + 16 * i - 8];
#pragma unroll
            for (int j = FULL ? 0 : M; j < 8; j++) mma_bf16(acc[j], hi.x, hi.y, lo.x, lo.y, sw[(j - M) & 7][2 * i], sw[(j - M) & 7][2 * i + 1]);
        }
        if (FULL) {
            ldsm_x4(&sw[7 - M][0], ub + o0 - (M + 1) * 256);
            if (M < 3) ldsm_x4(&sw[7 - M][4], ub + o1 - (M + 1) * 256);
        }
    }
    if (first_half) {
        const uint2 hi = Tp[512], lo = Tp[504];
#pragma unroll
        for (int j = FULL ? 0 : 4; j < 8; j++) mma_bf16(acc[j], hi.x, hi.y, lo.x, lo.y, sw[(j - 4) & 7][0], sw[(j - 4) & 7][1]);
    }
}
__device__ __forceinline__ uint32_t fin2(uint32_t y, uint32_t u, uint32_t dk) {
    typedef __nv_bfloat162 b2;
    const b2 r = __hadd2_rn(*reinterpret_cast<const b2*>(&y), __hmul2_rn(*reinterpret_cast<const b2*>(&u), *reinterpret_cast<const b2*>(&dk)));
    return *reinterpret_cast<const uint32_t*>(&r);
}
__global__ void __launch_bounds__(CV_THREADS, 1) conv_kernel(const bf16* __restrict__ Dskip, int layer, const uint4* __restrict__ piv, const float4* __restrict__ sum, const bf16* __restrict__ x1T,
                                                             bf16* __restrict__ dst, const uint4* __restrict__ tap, bf16* __restrict__ yT, const __grid_constant__ CUtensorMap tmOut) {
    extern __shared__ __align__(128) unsigned char sm[];
    SPAN(3 + 4 * layer, 0);
    bf16* Us = reinterpret_cast<bf16*>(sm + CV_SM_U);
    bf16* Xs = reinterpret_cast<bf16*>(sm + CV_SM_X);
    bf16* Ys = reinterpret_cast<bf16*>(sm + CV_SM_Y);
    const int tid = threadIdx.x, lane = tid & 31, warp = __shfl_sync(~0u, tid >> 5, 0);
    const int d0 = blockIdx.x * CV_CPB, tile = blockIdx.x; (void)tile;
    const int g = lane >> 2, ti = lane & 3;
    const int e = g - 2 * ti;
    uint32_t lds_off[4];
    uint32_t off2, off3, offc;
    {
        const int mat = lane >> 3, r = lane & 7;
#pragma unroll
        for (int pr = 0; pr < 4; pr++) {
            const int iw = 2 * pr + (mat >> 1), half = mat & 1;
            const int chunk = (UPADF - 16 * iw + 16 * r + 8 * half) >> 3;
            lds_off[pr] = (uint32_t)((chunk ^ ((chunk >> 3) & 1)) * 16);
        }
        const int j2 = 13 + r + 8 * (mat >> 1), j3 = j2 + 2, i0 = 8 * (mat & 1);
        off2 = (j2 & 1) ? BX_3 + (4 * j2 + i0 + 84) * 2 : BX_5 + (4 * j2 + i0 + 80) * 2;
        off3 = ((j3 & 1) ? BX_7 : BX_9) + (8 * j3 + i0 + 136) * 2;
        const int cc = (UPADF + 16 * (r + (mat >> 1)) + i0) >> 3;
        offc = (uint32_t)((cc ^ ((cc >> 3) & 1)) * 16);
    }
#define CV_WX 0
    const int wv = warp ^ CV_WX;
    const uint32_t rtab = wv < 8 ? (wv < 4 ? 0x0B090200u : 0x0C0A0301u) : (wv < 12 ? 0x13111008u : 0x1412241Cu);
    const int rl = (rtab >> (8 * (warp & 3))) & 0xff, type = rl >> 3, c = rl & 7;
    const int H = (type == 1 || type == 2) ? 1 : 0, T0 = 8 * H;
    uint32_t toff = CV_SM_T + c * TAPB + (TPAD + e) * 8;
    uint32_t ubase = smem_u32(Us + c * ULEN);
    const uint32_t bbase = smem_u32(sm + CV_SM_B + c * BX_LEN);
    uint32_t rd0, rd1;
    {
        const uint32_t rstart = wv < 8 ? (wv < 4 ? 0x02000000u : 0x06040000u) : (wv < 12 ? 0x0C0B0A08u : 0x1E1D150Fu);
        const uint32_t rcount = wv < 8 ? 0x02020000u : (wv < 12 ? 0x03010102u : 0x01010806u);
        rd0 = (rstart >> (8 * (warp & 3))) & 0xff; rd1 = rd0 + ((rcount >> (8 * (warp & 3))) & 0xff);
    }
    asm volatile("" : "+r"(lds_off[0]), "+r"(lds_off[1]), "+r"(lds_off[2]), "+r"(lds_off[3]), "+r"(ubase), "+r"(toff), "+r"(rd0), "+r"(rd1));
    const uint2* Tc = reinterpret_cast<const uint2*>(sm + toff);
    TSTAMP1X(9, 256);
    unsigned short dskr;
    asm volatile("ld.global.nc.u16 %0, [%1];" : "=h"(dskr) : "l"(Dskip + d0 + min(lane, CV_CPB - 1)));
    if (tid >= 256) {
        const int t2 = tid - 256;
        if (t2 == 0) {
            mbar_init(smem_u32(sm + CV_SM_CNT) + 104, 1);
            asm volatile("fence.mbarrier_init.release.cluster;" ::: "memory");
            mbar_expect_tx(smem_u32(sm + CV_SM_CNT) + 104, CV_CPB * 2048);
            bulk_load(smem_u32(sm + CV_SM_O), tap + d0 * 128, CV_CPB * 2048, smem_u32(sm + CV_SM_CNT) + 104);
        } else if (lane == 0) {
            mbar_init(smem_u32(sm + CV_SM_CNT) + 16 * (warp - 9), warp == 15 ? 16 : 1);
            if (warp < 15) mbar_init(smem_u32(sm + CV_SM_CNT) + 16 * (warp - 9) + 8, 1);
            else if (layer) prefetch_tmap(&tmOut);
        }
        if (t2 < 149) {
            const int k = t2;
            const int off = k < 18 ? BX_5 + 8 * k : k < 37 ? BX_3 + 8 * (k - 18) : k < 69 ? BX_9 + 8 * (k - 37) : k < 101 ? BX_7 + 8 * (k - 69)
                          : k < 133 ? 8 * (k - 101) : (UPADF + SEQ) * 2 + 8 * (k - 133);
#pragma unroll
            for (int c = 0; c < CV_CPB; c++) *reinterpret_cast<uint2*>(sm + (k < 101 ? CV_SM_B + c * BX_LEN : CV_SM_U + c * ULEN * 2) + off) = make_uint2(0, 0);
        }
        asm volatile("bar.sync 1, 256;" ::: "memory");
        TSTAMP1X(10, 256);
        mbar_wait(smem_u32(sm + CV_SM_CNT) + 104, 0);
        TSTAMP1X(11, 256);
#pragma unroll 1
        for (int r = t2; r < 392; r += 256) {
            const bool dd = r < 272, cc = r >= 368;
            const uint32_t* E2 = reinterpret_cast<const uint32_t*>(sm + CV_SM_O) + (dd ? r + 3 : r < 320 ? 301 + 2 * (r - 272) : cc ? 417 : 401 + 2 * (r - 320));
            const uint32_t* E3 = E2 + (dd ? 4 : cc ? 0 : 1);
            const uint32_t s0 = !cc ? 0x7610u : r == 382 ? 0x1044u : 0x4444u, s1 = !cc ? 0x7610u : r == 378 ? 0x1044u : 0x4444u;
            const uint32_t s2 = !cc ? 0x1032u : r == 381 ? 0x4410u : 0x4444u, s3 = !cc ? 0x1032u : r == 377 ? 0x4410u : 0x4444u;
            uint32_t w[CV_CPB][4];
#pragma unroll
            for (int c = 0; c < CV_CPB; c++) { w[c][0] = E2[512 * c]; w[c][1] = E2[512 * c + 1]; w[c][2] = E3[512 * c]; w[c][3] = E3[512 * c + 1]; }
#pragma unroll
            for (int c = 0; c < CV_CPB; c++) {
                const uint32_t a = __byte_perm(w[c][3], w[c][2], s1), b = __byte_perm(w[c][1], w[c][0], s2);
                *reinterpret_cast<uint4*>(sm + CV_SM_T + c * TAPB + r * 16) =
                    make_uint4(__byte_perm(w[c][1], w[c][0], s0), dd || cc ? a : b, dd || cc ? b : a, __byte_perm(w[c][3], w[c][2], s3));
            }
        }
        TSTAMP1X(12, 256);
        if (layer == 0) {
#pragma unroll
            for (int c = 0; c < CV_CPB; c++) reinterpret_cast<uint4*>(yT + (size_t)(d0 + c) * XCP)[t2] = make_uint4(~0u, ~0u, ~0u, ~0u);
        }
        pdl_sync();
        if (layer && blockIdx.x == 0 && t2 == 0) g_epoch = ld_epoch();
    } else {
        const uint4* ppv = piv + tid;
        const float4* psv = sum + tid;
        const uint2* pxv = reinterpret_cast<const uint2*>(x1T + (size_t)d0 * XCP) + (tid >> 4) * 32 + (tid & 15);
        asm volatile("st.shared.u64 [%0], %1;" ::"r"(smem_u32(Ys) + tid * 8), "l"((uint64_t)ppv ^ (uint64_t)psv ^ (uint64_t)pxv) : "memory");
        pdl_sync();
        SPAN(3 + 4 * layer, 1);
        TSTAMP(0);
        if (threadIdx.x == 0) { GSTAMP(g_tim, 15); }
        float4 sv[4];
#pragma unroll
        for (int k = 0; k < 4; k++) sv[k] = CV_LD(psv + 256 * k);
        const uint4 pv = CV_LD(ppv);
        uint2 xe[CV_CPB], xo[CV_CPB];
#pragma unroll
        for (int c = 0; c < CV_CPB; c++) { xe[c] = CV_LDX(pxv + c * (XCP / 4)); xo[c] = CV_LDX(pxv + c * (XCP / 4) + 16); }
        uint32_t mw[4];
        float rs[8];
#pragma unroll
        for (int k = 0; k < 4; k++) {
            const uint32_t pw = k == 0 ? pv.x : k == 1 ? pv.y : k == 2 ? pv.z : pv.w;
            const float d0_ = sv[k].x * (1.0f / DM), d1_ = sv[k].z * (1.0f / DM);
            mw[k] = pack2(__uint_as_float(pw << 16) + d0_, __uint_as_float(pw & 0xffff0000u) + d1_);
            const uint32_t vr = pack2(fmaxf(fmaf(-d0_, d0_, sv[k].y * (1.0f / DM)), 0.f), fmaxf(fmaf(-d1_, d1_, sv[k].w * (1.0f / DM)), 0.f));
            const uint32_t ve = pack2(__uint_as_float(vr << 16) + 1e-5f, __uint_as_float(vr & 0xffff0000u) + 1e-5f);
            const uint32_t sd = pack2(sqrt_apx(__uint_as_float(ve << 16)), sqrt_apx(__uint_as_float(ve & 0xffff0000u)));
            rs[2 * k] = rcp_apx(__uint_as_float(sd << 16)); rs[2 * k + 1] = rcp_apx(__uint_as_float(sd & 0xffff0000u));
        }
        if (rs[0] != 123.f) TSTAMP(13);
        const int ch = tid + UPADF / 8, pch = ch ^ ((ch >> 3) & 1);
#pragma unroll
        for (int c = 0; c < CV_CPB; c++) {
            *reinterpret_cast<uint4*>(Xs + c * XLEN + tid * 8) = make_uint4(xe[c].x, xe[c].y, xo[c].x, xo[c].y);
            const uint32_t e0 = sub2(xe[c].x, mw[0]), e1 = sub2(xe[c].y, mw[1]), o0 = sub2(xo[c].x, mw[2]), o1 = sub2(xo[c].y, mw[3]);
            *reinterpret_cast<uint4*>(Us + c * ULEN + pch * 8) =
                make_uint4(pack2(__uint_as_float(e0 << 16) * rs[0], __uint_as_float(o0 << 16) * rs[4]), pack2(__uint_as_float(e0 & 0xffff0000u) * rs[1], __uint_as_float(o0 & 0xffff0000u) * rs[5]),
                           pack2(__uint_as_float(e1 << 16) * rs[2], __uint_as_float(o1 << 16) * rs[6]), pack2(__uint_as_float(e1 & 0xffff0000u) * rs[3], __uint_as_float(o1 & 0xffff0000u) * rs[7]));
        }
    }
    __syncthreads();
    TSTAMP(1);
#pragma unroll 1
    for (int rd = rd0; rd < (int)rd1; rd++) {
        const int i = 32 * rd + lane;
        if (i < CV_CPB * 193) {
            const int c = i / 193, chunk = i - c * 193 - 1, ch = chunk + UPADF / 8;
            const bf16* uc = Us + c * ULEN;
            const uint4 o = *reinterpret_cast<const uint4*>(uc + (ch ^ ((ch >> 3) & 1)) * 8);
            const uint2 lo = *reinterpret_cast<const uint2*>(uc + ((ch - 1) ^ (((ch - 1) >> 3) & 1)) * 8 + 4);
            const uint2 hi = *reinterpret_cast<const uint2*>(uc + ((ch + 1) ^ (((ch + 1) >> 3) & 1)) * 8);
            const uint32_t w[8] = {lo.x, lo.y, o.x, o.y, o.z, o.w, hi.x, hi.y};
            float v[16], b[8];
#pragma unroll
            for (int k = 0; k < 8; k++) { v[2 * k] = __uint_as_float(w[k] << 16); v[2 * k + 1] = __uint_as_float(w[k] & 0xffff0000u); }
            unsigned char* bx = sm + CV_SM_B + c * BX_LEN + chunk * 16;
#pragma unroll
            for (int k = 0; k < 8; k++) b[k] = v[k + 4] + (v[k + 3] + v[k + 5]);
            *reinterpret_cast<uint2*>(bx + BX_3 + 168) = make_uint2(pack2(b[0], b[1]), pack2(b[2], b[3]));
            *reinterpret_cast<uint2*>(bx + BX_3 + 176) = make_uint2(pack2(b[4], b[5]), pack2(b[6], b[7]));
#pragma unroll
            for (int k = 0; k < 8; k++) b[k] += v[k + 2] + v[k + 6];
            *reinterpret_cast<uint4*>(bx + BX_5 + 160) = make_uint4(pack2(b[0], b[1]), pack2(b[2], b[3]), pack2(b[4], b[5]), pack2(b[6], b[7]));
            if (chunk < 128) {
#pragma unroll
                for (int k = 0; k < 8; k++) b[k] += v[k + 1] + v[k + 7];
                *reinterpret_cast<uint4*>(bx + BX_7 + 272) = make_uint4(pack2(b[0], b[1]), pack2(b[2], b[3]), pack2(b[4], b[5]), pack2(b[6], b[7]));
#pragma unroll
                for (int k = 0; k < 8; k++) b[k] += v[k] + v[k + 8];
                *reinterpret_cast<uint4*>(bx + BX_9 + 272) = make_uint4(pack2(b[0], b[1]), pack2(b[2], b[3]), pack2(b[4], b[5]), pack2(b[6], b[7]));
            }
        }
    }
    __syncwarp();
    if (lane == 0) mbar_arrive(smem_u32(sm + CV_SM_CNT) + 96);
    TSTAMP(2);
    {
        float acc[8][4];
#pragma unroll
        for (int j = 0; j < 8; j++)
#pragma unroll
            for (int k = 0; k < 4; k++) acc[j][k] = 0.f;
#pragma unroll 1
        for (int pass = (type == 2 || type == 4) ? 1 : 0; pass < ((type == 1 || type == 3) ? 1 : 2); pass++) {
            const uint32_t o0 = pass ? lds_off[2] : lds_off[0], o1 = pass ? lds_off[3] : lds_off[1];
            if (H) direct_pass<true>(acc, ubase + T0 * 256, o0, o1, Tc + 64 * pass, pass == 0);
            else direct_pass<false>(acc, ubase, o0, o1, Tc + 64 * pass, pass == 0);
        }
        TSTAMP(6);
        mbar_wait(smem_u32(sm + CV_SM_CNT) + 96, 0);
        if (type != 1 && type != 4) {
            const uint32_t* w2 = reinterpret_cast<const uint32_t*>(sm + CV_SM_T + c * TAPB + TAP_W2) + (115 - 96) + 4 * g - 2 * ti;
            uint32_t f[10][2];
#pragma unroll
            for (int k = 0; k < 10; k++) { f[k][0] = w2[16 * k]; f[k][1] = w2[16 * k - 8]; }
            const uint32_t ab = bbase + off2 + (2 * T0 + 6) * 128;
            const int kmax = H ? 23 : 8;
            uint32_t a[3][4];
            ldsm_x4_t(a[0], ab);
            ldsm_x4_t(a[1], ab - 128);
#pragma unroll
            for (int kp = 0; kp < 24; kp++) {
                if (kp > kmax) break;
                if (kp < 22) ldsm_x4_t(a[(kp + 2) % 3], ab - min(kp + 2, kmax) * 128);
#pragma unroll
                for (int j = 0; j < 8; j++) {
                    const int ee = 2 * j - 14 + kp;
                    if (ee >= 0 && ee <= 9) mma_bf16(acc[j], a[kp % 3][0], a[kp % 3][1], a[kp % 3][2], a[kp % 3][3], f[ee][0], f[ee][1]);
                }
            }
        }
        TSTAMP(7);
        if (type != 2 && type != 4) {
            const uint32_t* w3 = reinterpret_cast<const uint32_t*>(sm + CV_SM_T + c * TAPB + TAP_W3) + (129 - 96) + 2 * (g - ti);
            uint32_t f[9][2];
#pragma unroll
            for (int k = 0; k < 9; k++) { f[k][0] = w3[16 * k]; f[k][1] = w3[16 * k - 8]; }
            const uint32_t ab = bbase + off3 + (T0 - 2) * 256;
            uint32_t a[3][4];
            ldsm_x4_t(a[0], ab);
            ldsm_x4_t(a[1], ab - H * 256);
#pragma unroll
            for (int kp = 0; kp < 9; kp++) {
                if (kp > T0) break;
                if (kp < 7) ldsm_x4_t(a[(kp + 2) % 3], ab - min(kp + 2, T0) * 256);
#pragma unroll
                for (int j = 0; j < 8; j++) {
                    const int dl = j - 7 + kp;
                    if (dl >= 0 && dl <= 8) mma_bf16(acc[j], a[kp % 3][0], a[kp % 3][1], a[kp % 3][2], a[kp % 3][3], f[dl][0], f[dl][1]);
                }
            }
            const uint2* Dc = reinterpret_cast<const uint2*>(sm + CV_SM_T + c * TAPB + TAP_C) + e;
            const uint2 h63 = Dc[16], h64 = Dc[32], l63 = Dc[8], l64 = Dc[24];
#pragma unroll
            for (int j = 0; j < 8; j++)
                if (j == 7 || H) {
                    uint32_t bq[4];
                    ldsm_x4(bq, ubase + offc + (T0 + j - 8) * 256);
                    mma_bf16(acc[j], h64.x, h64.y, l64.x, l64.y, bq[0], bq[1]);
                    mma_bf16(acc[j], h63.x, h63.y, l63.x, l63.y, bq[2], bq[3]);
                }
        }
        TSTAMP(8);
        int hh = (0x14 >> type) & 1;
        asm volatile("" : "+r"(hh));
        const bool hi_half = hh;
        if (type != 0) {
            const int pair = H ? c : 5;
            float4* give = reinterpret_cast<float4*>(sm + CV_SM_P + pair * 4096 + (hi_half ? 2048 : 0)) + lane;
            const float4* take = reinterpret_cast<const float4*>(sm + CV_SM_P + pair * 4096 + (hi_half ? 0 : 2048)) + lane;
            const uint32_t pb = smem_u32(sm + CV_SM_CNT) + pair * 16;
#pragma unroll
            for (int j = 0; j < 8; j++)
                asm volatile("{\n.reg .pred p;\nsetp.eq.s32 p, %5, %6;\n@p st.shared.v4.f32 [%0], {%1,%2,%3,%4};\n}"
                             ::"r"(smem_u32(give + 32 * (j & 3))), "f"(acc[j][0]), "f"(acc[j][1]), "f"(acc[j][2]), "f"(acc[j][3]), "r"(hh), "r"(j < 4 ? 1 : 0) : "memory");
            __syncwarp();
            if (lane == 0) mbar_arrive(pb + (hi_half ? 8 : 0));
            mbar_wait(pb + (hi_half ? 0 : 8), 0);
#pragma unroll
            for (int j = 0; j < 4; j++) {
                const float4 v = take[32 * j];
                acc[j][0] = (hi_half ? acc[j + 4][0] : acc[j][0]) + v.x; acc[j][1] = (hi_half ? acc[j + 4][1] : acc[j][1]) + v.y;
                acc[j][2] = (hi_half ? acc[j + 4][2] : acc[j][2]) + v.z; acc[j][3] = (hi_half ? acc[j + 4][3] : acc[j][3]) + v.w;
            }
        }
        const uint32_t dk = __shfl_sync(~0u, (uint32_t)dskr, c) * 0x10001u;
#pragma unroll 1
        for (int rnd = 0; rnd < (type == 0 ? 2 : 1); rnd++) {
            const int Q = 2 * H + (hi_half ? 1 : rnd);
            if (rnd) {
#pragma unroll
                for (int j = 0; j < 4; j++)
#pragma unroll
                    for (int k = 0; k < 4; k++) acc[j][k] = acc[j + 4][k];
            }
            const uint32_t ya = smem_u32(Ys + c * XLEN) + (128 * (4 * Q + (lane >> 4)) + 16 * (lane & 7) + 8 * ((lane >> 3) & 1)) * 2;
#pragma unroll
            for (int j = 0; j < 4; j += 2)
                asm volatile("stmatrix.sync.aligned.m8n8.x4.trans.shared.b16 [%0], {%1,%2,%3,%4};" ::"r"(ya + j * 256),
                             "r"(pack2(acc[j][0], acc[j][1])), "r"(pack2(acc[j][2], acc[j][3])),
                             "r"(pack2(acc[j + 1][0], acc[j + 1][1])), "r"(pack2(acc[j + 1][2], acc[j + 1][3])) : "memory");
            __syncwarp();
            uint4 yv[2], xv[2], uv[2];
#pragma unroll
            for (int k = 0; k < 2; k++) {
                const int t = 512 * Q + 256 * k + 8 * lane, cu = (t + UPADF) >> 3;
                yv[k] = *reinterpret_cast<const uint4*>(Ys + c * XLEN + t);
                xv[k] = *reinterpret_cast<const uint4*>(Xs + c * XLEN + t);
                uv[k] = *reinterpret_cast<const uint4*>(Us + c * ULEN + (cu ^ ((cu >> 3) & 1)) * 8);
            }
#pragma unroll
            for (int k = 0; k < 2; k++) {
                const uint32_t z0 = fin2(yv[k].x, uv[k].x, dk), z1 = fin2(yv[k].y, uv[k].y, dk), z2 = fin2(yv[k].z, uv[k].z, dk), z3 = fin2(yv[k].w, uv[k].w, dk);
                if (layer)
                    asm volatile("st.relaxed.gpu.global.v4.u32 [%0], {%1,%2,%3,%4};" ::"l"(dst + (size_t)(d0 + c) * XCP + 512 * Q + 256 * k + 8 * lane),
                                 "r"(add2(__byte_perm(xv[k].x, xv[k].z, 0x5410), z0)), "r"(add2(__byte_perm(xv[k].x, xv[k].z, 0x7632), z1)),
                                 "r"(add2(__byte_perm(xv[k].y, xv[k].w, 0x5410), z2)), "r"(add2(__byte_perm(xv[k].y, xv[k].w, 0x7632), z3)) : "memory");
                else {
                    uint2* dp = reinterpret_cast<uint2*>(dst + (size_t)(d0 + c) * XCP + 512 * Q + 256 * k) + (lane >> 4) * 32 + (lane & 15);
                    dp[0] = make_uint2(add2(xv[k].x, __byte_perm(z0, z1, 0x5410)), add2(xv[k].y, __byte_perm(z2, z3, 0x5410)));
                    dp[16] = make_uint2(add2(xv[k].z, __byte_perm(z0, z1, 0x7632)), add2(xv[k].w, __byte_perm(z2, z3, 0x7632)));
                }
            }
        }
        TSTAMP(4);
        if (layer == 1) {
            const int mb = blockIdx.x >> 3, cg = blockIdx.x & 7;
            const bf16* src = dst + (size_t)(cg * 80 + (tid >> 4)) * XCP + mb * 128 + (tid & 15) * 8;
            uint32_t v[3][4];
            __syncthreads();
            TSTAMP(5);
            uint32_t todo = warp < 8 ? 7 : 3;
#pragma unroll 1
            for (int it = 0; it < SPIN_MAX; it++) {
#pragma unroll
                for (int k = 0; k < 3; k++)
                    if (todo >> k & 1)
                        asm volatile("ld.relaxed.gpu.global.v4.u32 {%0,%1,%2,%3}, [%4];" : "=r"(v[k][0]), "=r"(v[k][1]), "=r"(v[k][2]), "=r"(v[k][3]) : "l"(src + k * (32 * XCP)) : "memory");
#pragma unroll
                for (int k = 0; k < 3; k++)
                    if ((todo >> k & 1) && v[k][0] != ~0u && v[k][1] != ~0u && v[k][2] != ~0u && v[k][3] != ~0u) {
                        *reinterpret_cast<uint4*>(sm + (32 * k + (tid >> 4)) * 272 + (tid & 15) * 16) = make_uint4(v[k][0], v[k][1], v[k][2], v[k][3]);
                        todo ^= 1u << k;
                    }
                if (!todo) break;
                __nanosleep(CV_SLEEP);
            }
            __syncthreads();
            uint32_t w[12];
#pragma unroll
            for (int k = 0; k < 3; k++) ldsm_x4(&w[4 * k], smem_u32(sm) + min(32 * k + lane, 79) * 272 + warp * 16);
            const uint32_t ot = smem_u32(sm + CV_SM_O) + warp * 1280, oa = ot + (lane & 7) * 160 + (lane >> 3) * 16;
            stsm_x4_t(oa, w[0], w[1], w[2], w[3]);
            stsm_x4_t(oa + 64, w[4], w[5], w[6], w[7]);
            asm volatile("stmatrix.sync.aligned.m8n8.x2.trans.shared.b16 [%0], {%1,%2};" ::"r"(oa + 128), "r"(w[8]), "r"(w[9]) : "memory");
            fence_async_smem();
            __syncwarp();
            if (lane == 0) tma_store_2d(&tmOut, cg * 80, mb * 128 + 8 * warp, ot);
        }
    }
    TSTAMP(3);
    GSTAMP(g_tim, 14);
    SPAN(3 + 4 * layer, 3);
}

__device__ __forceinline__ void wgmma_fence() { asm volatile("wgmma.fence.sync.aligned;" ::: "memory"); }
__device__ __forceinline__ void wgmma_commit() { asm volatile("wgmma.commit_group.sync.aligned;" ::: "memory"); }
template <int N> __device__ __forceinline__ void wgmma_wait() { asm volatile("wgmma.wait_group.sync.aligned %0;" ::"n"(N) : "memory"); }
__device__ __forceinline__ uint64_t make_desc(uint32_t addr, uint32_t lbo, uint32_t sbo, uint32_t mode) {
    return (uint64_t)((addr & 0x3FFFF) >> 4) | ((uint64_t)(lbo >> 4) << 16) | ((uint64_t)(sbo >> 4) << 32) | ((uint64_t)mode << 62);
}
template <int TA, int TB>
__device__ __forceinline__ void wgmma_n240(float (&d)[120], uint64_t da, uint64_t db, int acc) {
    asm volatile("{\n.reg .pred p;\nsetp.ne.b32 p, %124, 0;\nwgmma.mma_async.sync.aligned.m64n240k16.f32.bf16.bf16 {%0,%1,%2,%3,%4,%5,%6,%7,%8,%9,%10,%11,%12,%13,%14,%15,%16,%17,%18,%19,%20,%21,%22,%23,%24,%25,%26,%27,%28,%29,%30,%31,%32,%33,%34,%35,%36,%37,%38,%39,%40,%41,%42,%43,%44,%45,%46,%47,%48,%49,%50,%51,%52,%53,%54,%55,%56,%57,%58,%59,%60,%61,%62,%63,%64,%65,%66,%67,%68,%69,%70,%71,%72,%73,%74,%75,%76,%77,%78,%79,%80,%81,%82,%83,%84,%85,%86,%87,%88,%89,%90,%91,%92,%93,%94,%95,%96,%97,%98,%99,%100,%101,%102,%103,%104,%105,%106,%107,%108,%109,%110,%111,%112,%113,%114,%115,%116,%117,%118,%119}, %120, %121, p, 1, 1, %122, %123;\n}"
                 : "+f"(d[0]), "+f"(d[1]), "+f"(d[2]), "+f"(d[3]), "+f"(d[4]), "+f"(d[5]), "+f"(d[6]), "+f"(d[7]), "+f"(d[8]), "+f"(d[9]), "+f"(d[10]), "+f"(d[11]), "+f"(d[12]), "+f"(d[13]), "+f"(d[14]), "+f"(d[15]), "+f"(d[16]), "+f"(d[17]), "+f"(d[18]), "+f"(d[19]), "+f"(d[20]), "+f"(d[21]), "+f"(d[22]), "+f"(d[23]), "+f"(d[24]), "+f"(d[25]), "+f"(d[26]), "+f"(d[27]), "+f"(d[28]), "+f"(d[29]), "+f"(d[30]), "+f"(d[31]), "+f"(d[32]), "+f"(d[33]), "+f"(d[34]), "+f"(d[35]), "+f"(d[36]), "+f"(d[37]), "+f"(d[38]), "+f"(d[39]), "+f"(d[40]), "+f"(d[41]), "+f"(d[42]), "+f"(d[43]), "+f"(d[44]), "+f"(d[45]), "+f"(d[46]), "+f"(d[47]), "+f"(d[48]), "+f"(d[49]), "+f"(d[50]), "+f"(d[51]), "+f"(d[52]), "+f"(d[53]), "+f"(d[54]), "+f"(d[55]), "+f"(d[56]), "+f"(d[57]), "+f"(d[58]), "+f"(d[59]), "+f"(d[60]), "+f"(d[61]), "+f"(d[62]), "+f"(d[63]), "+f"(d[64]), "+f"(d[65]), "+f"(d[66]), "+f"(d[67]), "+f"(d[68]), "+f"(d[69]), "+f"(d[70]), "+f"(d[71]), "+f"(d[72]), "+f"(d[73]), "+f"(d[74]), "+f"(d[75]), "+f"(d[76]), "+f"(d[77]), "+f"(d[78]), "+f"(d[79]), "+f"(d[80]), "+f"(d[81]), "+f"(d[82]), "+f"(d[83]), "+f"(d[84]), "+f"(d[85]), "+f"(d[86]), "+f"(d[87]), "+f"(d[88]), "+f"(d[89]), "+f"(d[90]), "+f"(d[91]), "+f"(d[92]), "+f"(d[93]), "+f"(d[94]), "+f"(d[95]), "+f"(d[96]), "+f"(d[97]), "+f"(d[98]), "+f"(d[99]), "+f"(d[100]), "+f"(d[101]), "+f"(d[102]), "+f"(d[103]), "+f"(d[104]), "+f"(d[105]), "+f"(d[106]), "+f"(d[107]), "+f"(d[108]), "+f"(d[109]), "+f"(d[110]), "+f"(d[111]), "+f"(d[112]), "+f"(d[113]), "+f"(d[114]), "+f"(d[115]), "+f"(d[116]), "+f"(d[117]), "+f"(d[118]), "+f"(d[119])
                 : "l"(da), "l"(db), "n"(TA), "n"(TB), "r"(acc));
}

__device__ __forceinline__ void wgmma_n80(float (&d)[40], uint64_t da, uint64_t db, int acc) {
    asm volatile("{\n.reg .pred p;\nsetp.ne.b32 p, %42, 0;\nwgmma.mma_async.sync.aligned.m64n80k16.f32.bf16.bf16 {%0,%1,%2,%3,%4,%5,%6,%7,%8,%9,%10,%11,%12,%13,%14,%15,%16,%17,%18,%19,%20,%21,%22,%23,%24,%25,%26,%27,%28,%29,%30,%31,%32,%33,%34,%35,%36,%37,%38,%39}, %40, %41, p, 1, 1, 0, 0;\n}"
                 : "+f"(d[0]), "+f"(d[1]), "+f"(d[2]), "+f"(d[3]), "+f"(d[4]), "+f"(d[5]), "+f"(d[6]), "+f"(d[7]), "+f"(d[8]), "+f"(d[9]), "+f"(d[10]), "+f"(d[11]), "+f"(d[12]), "+f"(d[13]), "+f"(d[14]), "+f"(d[15]), "+f"(d[16]), "+f"(d[17]), "+f"(d[18]), "+f"(d[19]), "+f"(d[20]), "+f"(d[21]), "+f"(d[22]), "+f"(d[23]), "+f"(d[24]), "+f"(d[25]), "+f"(d[26]), "+f"(d[27]), "+f"(d[28]), "+f"(d[29]), "+f"(d[30]), "+f"(d[31]), "+f"(d[32]), "+f"(d[33]), "+f"(d[34]), "+f"(d[35]), "+f"(d[36]), "+f"(d[37]), "+f"(d[38]), "+f"(d[39])
                 : "l"(da), "l"(db), "r"(acc));
}

constexpr int A1_THREADS = 384;
constexpr int A1_NST = 4;
#define A1_SKEW 8
constexpr int A1_STAGE = 16384 + WQ_STAGE;
constexpr int A1_KVP = 336;
constexpr int A1_SM_KV = 2 * A1_STAGE;
constexpr int A1_SM_BAR = A1_NST * A1_STAGE;
constexpr int A1_SM_RS = A1_SM_BAR + 512;
constexpr int A1_SM_W0 = A1_SM_BAR + 3072, A1_SM_W3 = A1_SM_BAR - 3 * WOB, A1_SM_A1 = 2 * WOB, A1_SM_A0 = A1_SM_A1 + 61440;
constexpr int A1_SM_XA = A1_SM_W0 + 2 * WOB, A1_SM_XB = A1_SM_XA + 2048;
constexpr int A1_SMEM = A1_SM_W0 + 3 * WOB;
static_assert(A1_SM_W3 >= A1_SM_KV + 144 * A1_KVP && A1_SM_W3 % 128 == 0 && A1_SM_A1 % 1024 == 0 && A1_SM_A0 <= A1_SM_KV && A1_SM_A0 + 61440 <= A1_SM_W3 && A1_SMEM <= 232448, "layout");
__device__ __forceinline__ constexpr uint32_t wo_off(int h) { return h * WOB + (h < 3 ? A1_SM_W0 : h < 6 ? A1_SM_W3 - 3 * WOB : -6 * WOB); }
#define A1_FRED "red.relaxed.gpu.global.add.u32"
#define A1_FLD "ld.acquire.gpu.global.u32"
#define ST_SLEEP 20
#define ST_SLEEP0 300
#define WO_LATE bar_done
#define A1_P0 2
#define A1_PW (kb - 2)
#define A1_FSPIN SPIN_MAX
#define A1_FSLEEP 40
#define A1_WOAT 6

template <int L>
__device__ __forceinline__ void a1_mainloop(float (&acc)[120], uint32_t sbase, uint32_t bars, int wg, int tile) {
    constexpr int layer = L; (void)layer;
    const uint64_t da0 = L ? make_desc(sbase + wg * 8192, 8192, 1024, 1) : make_desc(sbase + wg * 8192, 16, 1024, 1), db0 = make_desc(sbase + 16384, 16, 1024, 1);
#pragma unroll 1
    for (int t = 0;; t++) {
        const int st = t % A1_NST;
        mbar_wait(bars + 8 * st, (t / A1_NST) & 1);
        if (t == A1_SKEW && wg == 0) mbar_wait(bars + 160, 0);
        TSTAMP3(1 + t);
        wgmma_fence();
#pragma unroll
        for (int kk = 0; kk < 4; kk++) wgmma_n240<L, 0>(acc, da0 + (uint32_t)(st * (A1_STAGE / 16) + kk * (L ? 128 : 2)), db0 + (uint32_t)(st * (A1_STAGE / 16) + kk * 2), kk ? 1 : t);
        wgmma_commit();
        if (t == 9) break;
        if (t == A1_SKEW - 1 && wg == 0) wgmma_wait<0>(); else wgmma_wait<1>();
        if (t > 0 && (threadIdx.x & 127) == 0) {
            if (t != A1_SKEW || wg) mbar_arrive(bars + 8 * (A1_NST + (t - 1) % A1_NST));
            if (t == A1_SKEW - 1 && wg == 0) mbar_arrive(bars + 8 * (A1_NST + t % A1_NST));
        }
    }
}

__global__ void __launch_bounds__(A1_THREADS, 1) a1_kernel(const int layer, const bf16* __restrict__ x0, const unsigned char* __restrict__ wq, const unsigned char* wo,
                                                           float2* __restrict__ rsum, uint4* __restrict__ of, const __grid_constant__ CUtensorMap tmX,
                                                           const __grid_constant__ CUtensorMap tmR, const __grid_constant__ CUtensorMap tmX1, const __grid_constant__ TileTab tab) {
    extern __shared__ __align__(1024) unsigned char stg[];
    const uint32_t sbase = smem_u32(stg);
    const uint32_t bars = sbase + A1_SM_BAR;
    const uint32_t bar_stat = bars + 64, bar_kv = bars + 72, bar_rd = bars + 168;
    const uint32_t bar_wo = bars + 208, bar_done = bars + 216, bar_pv = bars + 224, bar_kvf = bars + 232, bar_f2 = bars + 248, bar_e2 = bars + 384, que = bars + 448;
    const int tid = threadIdx.x;
    const int w = __shfl_sync(~0u, tid >> 5, 0), wg = w >> 2;
    uint32_t smid, ns;
    asm volatile("mov.u32 %0, %smid;" : "=r"(smid));
    asm volatile("mov.u32 %0, %nsmid;" : "=r"(ns));
    const auto te = tab.e[ns == tab.ns ? smid : 132 + blockIdx.x];
    const int tile = te.tile, mb = te.mb, hg = te.hg;
    float2* rst = reinterpret_cast<float2*>(stg + A1_SM_RS) + 8;
    auto issue_w = [&](int it) { bulk_load(sbase + (it % A1_NST) * A1_STAGE + 16384, wq + te.woff + it * WQ_STAGE, WQ_STAGE, bars + 8 * (it % A1_NST)); };
    auto issue_x = [&](int it, int kb) {
        asm volatile("cp.async.bulk.tensor.5d.shared::cluster.global.mbarrier::complete_tx::bytes [%0], [%1, {%3, %3, %3, %4, %5}], [%2];"
                     ::"r"(sbase + (it % A1_NST) * A1_STAGE), "l"(&tmX), "r"(bars + 8 * (it % A1_NST)), "r"(0), "r"(mb), "r"(kb) : "memory");
    };
    if (w == 8 && tile < 128) {
        const bool one = elect();
        if (one) {
#pragma unroll
            for (int i = 0; i < A1_NST; i++) mbar_init(bars + 8 * i, 1);
            asm volatile("fence.mbarrier_init.release.cluster;" ::: "memory");
        }
        __syncwarp();
        asm volatile("bar.arrive 0, 384;" ::: "memory");
        if (one) {
#define PW asm volatile("griddepcontrol.wait;" ::: "memory");
            if (layer) { issue_w(0); PW issue_x(0, te.kb0); issue_x(1, te.kb0 + 1); }
            else { issue_x(0, te.kb0); issue_x(1, te.kb0 + 1); PW issue_w(0); }
            issue_w(1);
#pragma unroll
            for (int i = 0; i < A1_NST; i++) mbar_expect_tx(bars + 8 * i, A1_STAGE);
            asm volatile("griddepcontrol.launch_dependents;" ::: "memory");
#pragma unroll
            for (int kb = 2; kb < A1_P0; kb++) { issue_x(kb, te.kb0 + kb); issue_w(kb); }
            DBGC(34); DBGV(40, t_entry); DBGV(30, t_a); DBGV(31, t_b); DBGV(32, t_c); DBGV(38, t_d); DBGV(39, t_e);
        }
    }
    if (tile >= 128) { sm_idle(layer); return; }
    if (wg == 2) {
        if (w != 8) {
            if (tid == 320) { prefetch_tmap(&tmX); prefetch_tmap(&tmR); prefetch_tmap(&tmX1); }
            asm volatile("bar.sync 0, 384;" ::: "memory");
        }
        if (w == 9) {
            asm volatile("bar.arrive 3, 64;" ::: "memory");
            if (layer == 0) pdl_sync();
            float4 a[2] = {};
#pragma unroll
            for (int k = 0; k < 10; k++)
#pragma unroll
                for (int h = 0; h < 2; h++) {
                    const float4 v = __ldcg(reinterpret_cast<const float4*>(g_csp + k * 1920 + hg * 240) + min(tid - 288 + 32 * h, 59));
                    a[h].x += v.x; a[h].y += v.y; a[h].z += v.z; a[h].w += v.w;
                }
#pragma unroll
            for (int h = 0; h < 2; h++)
#pragma unroll
                for (int k = 0; k < 4; k++) {
                    const float c = 0.5f * (k == 0 ? a[h].x : k == 1 ? a[h].y : k == 2 ? a[h].z : a[h].w), c1 = c - rbf(c), c2 = c1 - rbf(c1);
                    *reinterpret_cast<uint4*>(stg + A1_SM_XB + (4 * min(tid - 288 + 32 * h, 59) + k) * 16) = make_uint4(pack2(c, c1), pack2(c2, 0.f), 0u, 0u);
                }
            fence_async_smem();
            __syncwarp();
            if (tid == 288) mbar_arrive(bar_stat);
#pragma unroll 4
            for (int k = 0; k < 40; k++) asm volatile("st.global.v4.u32 [%0], {%1,%1,%1,%1};" ::"l"(of + (mb * 8 + hg) * 1280 + 32 * k + (tid - 288)), "r"(~0u) : "memory");
            asm volatile("fence.acq_rel.gpu;" ::: "memory");
            asm volatile("fence.proxy.async.global;" ::: "memory");
            __syncwarp();
            if (tid == 288) mbar_arrive(bar_done);
            TSTAMP1T(9, 288);
        } else if (w == 8) {
            asm volatile("bar.sync 3, 64;" ::: "memory");
            if (elect()) {
#pragma unroll 1
                for (int kb = A1_P0; kb < 10; kb++) {
                    if (kb < A1_NST) mbar_wait(bars + 8 * A1_PW, 0);
                    else {
                        mbar_wait(bars + 8 * (A1_NST + kb % A1_NST), ((kb / A1_NST) - 1) & 1);
                        if (layer && kb < 9) mbar_wait(bar_rd + 8 * (kb - A1_NST), 0);
                        mbar_expect_tx(bars + 8 * (kb % A1_NST), A1_STAGE);
                    }
                    issue_x(kb, kb < 5 ? kb + te.kb0 : kb - te.kb0); issue_w(kb);
                    if (kb == A1_WOAT) {
                        mbar_expect_tx(bar_wo, 8 * WOB);
                        bulk_load(sbase + A1_SM_W0, wo + hg * 8 * WOB, 2 * WOB, bar_wo);
                    }
                }
                TSTAMP1T(6, 256);
                mbar_wait(bars + 8 * (A1_NST + 3), 1);
                bulk_load(sbase + A1_SM_W3, wo + (hg * 8 + 3) * WOB, 3 * WOB, bar_wo);
            }
            __syncwarp();
        } else {
            const int j = tid - 320;
            const uint32_t tag = ld_epoch();
            if (tid == 352) sm_started(layer);
            if (layer == 0) {
                const uint4* src = reinterpret_cast<const uint4*>(x0 + (size_t)(mb * 128 + hg * 16 + (j >> 2)) * DM);
                uint4 v[20];
#pragma unroll
                for (int k = 0; k < 20; k++) v[k] = __ldg(src + (j & 3) + 4 * k);
                const float p0 = __uint_as_float(__shfl_sync(~0u, v[0].x, j & 28) << 16);
                float s[2] = {0.f, 0.f}, q[2] = {0.f, 0.f};
#pragma unroll
                for (int k = 0; k < 20; k++) {
                    const uint32_t w[4] = {v[k].x, v[k].y, v[k].z, v[k].w};
#pragma unroll
                    for (int i = 0; i < 4; i++) {
                        const float a = __uint_as_float(w[i] << 16) - p0, b = __uint_as_float(w[i] & 0xffff0000u) - p0;
                        s[0] += a; s[1] += b; q[0] = fmaf(a, a, q[0]); q[1] = fmaf(b, b, q[1]);
                    }
                }
                float s0 = s[0] + s[1], q0 = q[0] + q[1];
#pragma unroll
                for (int o = 1; o <= 2; o <<= 1) { s0 += __shfl_xor_sync(~0u, s0, o); q0 += __shfl_xor_sync(~0u, q0, o); }
                if ((j & 3) == 0) {
                    const float d = s0 * (1.0f / DM);
                    const uint32_t ms = pack2(p0 + d, sqrt_apx(rbf(rbf(fmaxf(fmaf(-d, d, q0 * (1.0f / DM)), 0.f)) + 1e-5f)));
                    asm volatile("st.global.cg.u64 [%0], %1;" ::"l"(g_rstat + mb * 128 + (j & 4) * 16 + hg * 8 + (j >> 3)), "l"(tagw(ms, tag)) : "memory");
                    g_piv[mb * 128 + hg * 16 + ((j >> 2) & 8) + (j & 4) + ((j >> 3) & 3)] = __ushort_as_bfloat16((unsigned short)ms);
                }
            }
            float o[4];
            int row;
            if (layer == 0) {
                ulonglong2 v;
#pragma unroll 1
                for (int it = 0; it < SPIN_MAX; it++) {
                    v = ld_tag2(reinterpret_cast<const ulonglong2*>(g_rstat + mb * 128) + j);
                    if (tag_ok(v, tag)) break;
                    __nanosleep(100);
                }
                o[0] = __uint_as_float((uint32_t)v.x << 16); o[1] = rcp_apx(__uint_as_float((uint32_t)v.x & 0xffff0000u));
                o[2] = __uint_as_float((uint32_t)v.y << 16); o[3] = rcp_apx(__uint_as_float((uint32_t)v.y & 0xffff0000u));
                row = 2 * j;
            } else {
                const int ch = j & 7, kg = (j >> 3) & 3;
                const unsigned char* src = stg + (j >> 5) * 8192 + (hg & 3) * 2048;
                float s[8], q[8], p0[8];
#pragma unroll
                for (int i = 0; i < 8; i++) { s[i] = 0.f; q[i] = 0.f; }
#pragma unroll 1
                for (int it = 0; it < 5; it++) {
                    uint4 v[4];
                    mbar_wait(bars + 8 * (it % A1_NST), it / A1_NST);
#pragma unroll
                    for (int k = 0; k < 4; k++) v[k] = *reinterpret_cast<const uint4*>(src + (it % A1_NST) * A1_STAGE + (4 * k + kg) * 128 + ((ch ^ ((4 * k + kg) & 7)) << 4));
                    if (it == 0) {
                        const uint4 pv = *reinterpret_cast<const uint4*>(src + (ch << 4));
                        const uint32_t w[4] = {pv.x, pv.y, pv.z, pv.w};
#pragma unroll
                        for (int i = 0; i < 4; i++) { p0[2 * i] = __uint_as_float(w[i] << 16); p0[2 * i + 1] = __uint_as_float(w[i] & 0xffff0000u); }
                    }
                    asm volatile("" :: "r"(v[0].x), "r"(v[1].x), "r"(v[2].x), "r"(v[3].x), "f"(p0[0]) : "memory");
                    __syncwarp();
                    if ((tid & 31) == 0) mbar_arrive(bar_rd + 8 * it);
#pragma unroll
                    for (int k = 0; k < 4; k++) {
                        const uint32_t w[4] = {v[k].x, v[k].y, v[k].z, v[k].w};
#pragma unroll
                        for (int i = 0; i < 4; i++) {
                            const float a = __uint_as_float(w[i] << 16) - p0[2 * i], b = __uint_as_float(w[i] & 0xffff0000u) - p0[2 * i + 1];
                            s[2 * i] += a; s[2 * i + 1] += b; q[2 * i] = fmaf(a, a, q[2 * i]); q[2 * i + 1] = fmaf(b, b, q[2 * i + 1]);
                        }
                    }
                }
#pragma unroll
                for (int i = 0; i < 4; i++) {
                    const bool up = kg & 2;
                    const float ss = __shfl_xor_sync(~0u, up ? s[i] : s[i + 4], 16), qq = __shfl_xor_sync(~0u, up ? q[i] : q[i + 4], 16);
                    s[i] = (up ? s[i + 4] : s[i]) + ss; q[i] = (up ? q[i + 4] : q[i]) + qq; p0[i] = up ? p0[i + 4] : p0[i];
                }
#pragma unroll
                for (int i = 0; i < 2; i++) {
                    const bool up = kg & 1;
                    const float ss = __shfl_xor_sync(~0u, up ? s[i] : s[i + 2], 8), qq = __shfl_xor_sync(~0u, up ? q[i] : q[i + 2], 8);
                    s[i] = (up ? s[i + 2] : s[i]) + ss; q[i] = (up ? q[i + 2] : q[i]) + qq; p0[i] = up ? p0[i + 2] : p0[i];
                }
                uint4* gp = g_halo + 86016 + mb * 512 + j;
                const float d0 = s[0] * (1.0f / 80.0f), d1 = s[1] * (1.0f / 80.0f);
                asm volatile("st.relaxed.gpu.global.v4.f32 [%0], {%1,%2,%3,%4};" ::"l"(gp + hg * 64), "f"(p0[0] + d0), "f"(fmaxf(fmaf(-d0, s[0], q[0]), 0.f)), "f"(p0[1] + d1), "f"(fmaxf(fmaf(-d1, s[1], q[1]), 0.f)) : "memory");
                __nanosleep(ST_SLEEP0);
                uint32_t pw[8][4], todo = 0xff;
#pragma unroll 1
                for (int it = 0; it < SPIN_MAX; it++) {
#pragma unroll
                    for (int k = 0; k < 8; k++)
                        if (todo >> k & 1) asm volatile("ld.relaxed.gpu.global.v4.u32 {%0,%1,%2,%3}, [%4];" : "=r"(pw[k][0]), "=r"(pw[k][1]), "=r"(pw[k][2]), "=r"(pw[k][3]) : "l"(gp + k * 64) : "memory");
#pragma unroll
                    for (int k = 0; k < 8; k++)
                        if (__all_sync(~0u, pw[k][0] != ~0u && pw[k][1] != ~0u && pw[k][2] != ~0u && pw[k][3] != ~0u)) todo &= ~(1u << k);
                    if (!todo) break;
                    __nanosleep(ST_SLEEP);
                }
#pragma unroll
                for (int r = 0; r < 2; r++) {
                    float mean = 0.f, m2 = 0.f;
#pragma unroll
                    for (int k = 0; k < 8; k++) mean += __uint_as_float(pw[k][2 * r]);
                    mean *= 0.125f;
#pragma unroll
                    for (int k = 0; k < 8; k++) {
                        const float dm = __uint_as_float(pw[k][2 * r]) - mean;
                        m2 += fmaf(80.0f * dm, dm, __uint_as_float(pw[k][2 * r + 1]));
                    }
                    o[2 * r] = rbf(mean);
                    o[2 * r + 1] = rcp_apx(rbf(sqrt_apx(rbf(rbf(m2 * (1.0f / DM)) + 1e-5f))));
                }
                row = (j >> 5) * 64 + (j & 7) * 8 + ((j >> 3) & 3) * 2;
                if (hg == 0) *reinterpret_cast<uint32_t*>(g_piv + SEQ + mb * 128 + 2 * (row & 60) + 4 * (row >> 6) + (row & 3)) = __byte_perm(__float_as_uint(o[0]), __float_as_uint(o[2]), 0x7632);
            }
#pragma unroll
            for (int r = 0; r < 2; r++)
                *reinterpret_cast<uint4*>(stg + A1_SM_XA + (row + r) * 16) = make_uint4(__byte_perm(__float_as_uint(-o[2 * r]), 0, 0x3232), __float_as_uint(-o[2 * r]) >> 16, 0u, 0u);
            *reinterpret_cast<float4*>(rst + row + (row >> 6) * 8) = make_float4(o[0], o[1], o[2], o[3]);
            fence_async_smem();
            TSTAMP1T(7, 320);
            if (tid == 320) DBGC(44);
            __syncwarp();
            if ((tid & 31) == 0) mbar_arrive(bar_stat);
        }
        if (tid == 320) DBGCAL(0);
        if (tid == 352) {
            mbar_wait(WO_LATE, 0);
            mbar_wait(bar_done, 0);
            bulk_load(sbase, wo + (hg * 8 + 6) * WOB, 2 * WOB, bar_wo);
            bulk_load(sbase + A1_SM_W0 + 2 * WOB, wo + (hg * 8 + 2) * WOB, WOB, bar_wo);
        }
        if (w < 10) {
            const int cw = w - 8;
            const uint32_t* fl = reinterpret_cast<const uint32_t*>(rsum + 2 * SEQ) + (((layer * 16 + mb) * 2 + cw) * 8 + (tid & 7)) * FSTR;
            const unsigned char* src = reinterpret_cast<const unsigned char*>(of) + mb * 163840 + cw * 10240 + (tid & 7) * 20480;
            const uint32_t sl = sbase + (cw ? A1_SM_A1 : A1_SM_A0);
            mbar_wait(cw ? bar_done : bar_kvf, 0);
            if ((tid & 31) == 0) {
                mbar_expect_tx(bar_f2 + 64 * cw + 64, 10240);
                tma_load_3d(sl + 51200, &tmR, layer ? 0 : hg * 80, layer ? hg * 80 : mb * 64, layer ? mb * 2 + cw : cw, bar_f2 + 64 * cw + 64);
            }
            __syncwarp();
            uint32_t pend = 0xffu & ~(1u << hg), v = 0;
            const uint32_t bo = wo_off((tid & 7) + ((tid & 7) < hg)) >> 4, lt = (1u << (tid & 31)) - 1;
#pragma unroll 1
            for (int it = 0; pend && it < 2 * SPIN_MAX; it++) {
                if (v != 4 && (pend >> (tid & 31) & 1)) asm volatile(A1_FLD " %0, [%1];" : "=r"(v) : "l"(fl) : "memory");
                uint32_t fr;
                asm volatile("{\n.reg .pred p;\nmbarrier.test_wait.parity.shared::cta.b64 p, [%1], 0;\nselp.b32 %0, 1, 0, p;\n}" : "=r"(fr) : "r"(bar_e2 + 16 * cw + (tid & 1) * 8) : "memory");
                fr = __ballot_sync(~0u, fr);
                uint32_t m = __ballot_sync(~0u, v == 4 || it >= A1_FSPIN) & pend;
                const int q = 8 - __popc(pend) + __popc(m & lt);
                m &= __ballot_sync(~0u, q < ((fr & 2) ? 8 : (fr & 1) ? 7 : 5));
                pend ^= m;
                if (m >> (tid & 31) & 1) DBGC(12 + cw * 8 + (tid & 7));
                if (!m) __nanosleep(A1_FSLEEP);
                else asm volatile("fence.proxy.async.global;" ::: "memory");
                if (m >> (tid & 31) & 1) {
                    bulk_load(q == 7 && !cw ? sbase + A1_SM_W0 : sl + (q < 6 ? q : q - 6) * 10240, src, 10240, bar_f2 + 64 * cw + 8 * q);
                    asm volatile("st.shared.u32 [%0], %1;" ::"r"(que + 32 * cw + 4 * q), "r"(bo) : "memory");
                    mbar_expect_tx(bar_f2 + 64 * cw + 8 * q, 10240);
                    DBGC(44 + cw * 8 + q);
                }
                __syncwarp();
            }
        }
    } else {
        if (tid == 0) {
            mbar_init(bar_stat, 3);
#pragma unroll
            for (int i = 0; i < 8; i++) mbar_init(bar_kv + 8 * i, 1);
            mbar_init(bars + 144, 1);
            mbar_init(bars + 160, 1);
#pragma unroll
            for (int i = 0; i < 5; i++) mbar_init(bar_rd + 8 * i, 2);
            asm volatile("fence.mbarrier_init.release.cluster;" ::: "memory");
        } else if (tid == 32) {
            mbar_init(bar_wo, 1); mbar_init(bar_done, 3); mbar_init(bar_pv, 4); mbar_init(bar_kvf, 8); mbar_init(bars + 240, 4);
#pragma unroll
            for (int i = 0; i < 4; i++) { mbar_init(bar_e2 + 8 * i, i == 1 ? 2 : 1); mbar_init(bars + 8 * (A1_NST + i), 2); }
            asm volatile("fence.mbarrier_init.release.cluster;" ::: "memory");
        } else if (tid == 64) {
#pragma unroll
            for (int i = 1; i <= 16; i++) mbar_init(bar_f2 + 8 * i, 1);
            asm volatile("fence.mbarrier_init.release.cluster;" ::: "memory");
        }
        asm volatile("bar.sync 0, 384;" ::: "memory");
        SPAN(1 + 4 * layer, 0);
        constexpr int on = 1;
        float acc[120];
        const int lane = tid & 31, warp = w & 7, g = lane >> 2, t = lane & 3;
        if (on) {
            SPAN(1 + 4 * layer, 1);
            TSTAMP1(0);
            if (threadIdx.x == 0) { GSTAMP(g_tim1, 15); }
            TSTAMP3(0);
            if (tid == 0) TSTAMP2(0);
            TSTAMP4(0);
            if (tid == 0) DBGC(60);
            if (layer == 0) a1_mainloop<0>(acc, sbase, bars, wg, tile); else a1_mainloop<1>(acc, sbase, bars, wg, tile);
            uint32_t ok;
            asm volatile("{\n.reg .pred p;\nmbarrier.test_wait.parity.shared::cta.b64 p, [%1], 0;\nselp.b32 %0, 1, 0, p;\n}" : "=r"(ok) : "r"(bar_stat) : "memory");
            if (tid == 128 && !ok) mbar_arrive(bars + 160);
            __syncwarp();
            mbar_wait(bar_stat, 0);
            wgmma_fence();
            wgmma_n240<0, 0>(acc, make_desc(sbase + A1_SM_XA + wg * 1024, 0, 128, 0), make_desc(sbase + A1_SM_XB, 0, 128, 0), 1);
            wgmma_commit();
            if (tid == 128 && ok) mbar_arrive(bars + 160);
            mbar_wait(bars + 8 * (A1_NST + 3), 1);
        }
        const float2* rw = rst + 16 * warp + 8 * wg;
        const float rb0 = rw[g + 8].y, ra = rw[g].y * 0.22360679774997896f, rb = rb0 * 0.22360679774997896f;
        wgmma_wait<0>();
        if ((tid & 127) == 0) mbar_arrive(bar_done);
        TSTAMP1(2);
        TSTAMP1T(13, 224);
        if ((tid & 127) == 0) DBGC(62 - wg);
        uint32_t f[2][30];
#pragma unroll
        for (int j = 10; j < 30; j++) f[1][j] = pack2(acc[4 * j + 2], acc[4 * j + 3]);
        if ((warp & 3) == 3) {
            uint4* hout = g_halo + (((layer * 16 + mb) * 8 + hg) * 2 + wg) * 168;
#pragma unroll
            for (int j = 0; j < 20; j += 4)
                asm volatile("st.relaxed.gpu.global.v4.u32 [%0], {%1,%2,%3,%4};" ::"l"(hout + 8 * j + lane), "r"(f[1][10 + j]), "r"(f[1][11 + j]), "r"(f[1][12 + j]), "r"(f[1][13 + j]) : "memory");
            if (t == 0) asm volatile("st.relaxed.gpu.global.f32 [%0], %1;" ::"l"(reinterpret_cast<float*>(hout + 160) + g), "f"(rb0) : "memory");
        }
        TSTAMP1T(12, 224);
        const uint32_t kvw = sbase + A1_SM_KV + (16 * warp + 8 * wg) * A1_KVP;
        const uint32_t mrow = kvw + (lane & 7) * A1_KVP + (lane >> 3) * 16;
#pragma unroll
        for (int j = 0; j < 20; j += 4) stsm_x4(mrow + 16 * A1_KVP + 16 * j, f[1][10 + j], f[1][11 + j], f[1][12 + j], f[1][13 + j]);
        __syncwarp();
        if (lane == 0 && (warp & 3) != 3) mbar_arrive(bar_kv + 8 * (warp + 1));
#pragma unroll
        for (int j = 0; j < 30; j++) f[0][j] = pack2(acc[4 * j], acc[4 * j + 1]);
        stsm_x4(mrow + 8 * A1_KVP + 160, f[0][20], f[0][21], f[0][22], f[0][23]);
        stsm_x4(mrow + 8 * A1_KVP + 224, f[0][24], f[0][25], f[0][26], f[0][27]);
        asm volatile("stmatrix.sync.aligned.m8n8.x2.shared.b16 [%0], {%1,%2};" ::"r"(mrow + 8 * A1_KVP + 288), "r"(f[0][28]), "r"(f[0][29]) : "memory");
#pragma unroll
        for (int j = 0; j < 10; j++) f[1][j] = pack2(acc[4 * j + 2], acc[4 * j + 3]);
        __syncwarp();
        uint32_t vb[10][2], vp[12], kp[12];
#pragma unroll
        for (int j = 0; j < 10; j += 2) ldsm_x4_t(&vb[j][0], kvw + (8 + (lane & 15)) * A1_KVP + 160 + (lane >> 4) * 16 + 16 * j);
        const bool up0 = 2 * t > g, up1 = 2 * t + 1 > g, edge = (mb | (warp & 3)) == 0;
        float rk[4];
        auto above = [&]() {
            mbar_wait(bar_kv + 8 * warp, 0);
#pragma unroll
            for (int j = 0; j < 12; j += 4) ldsm_x4(&kp[j], mrow + 16 * j);
            rk[0] = rw[2 * t - (up0 ? 8 : 0)].y; rk[1] = rw[2 * t + 1 - (up1 ? 8 : 0)].y;
#pragma unroll
            for (int j = 0; j < 12; j += 4) ldsm_x4_t(&vp[j], mrow + 160 + 16 * j - (j == 8 ? (lane & 16) * 2 : 0));
            __syncwarp();
            if (lane == 0) mbar_arrive(bar_kvf);
        };
        auto halo = [&]() {
            if (lane == 0) mbar_arrive(bar_kvf);
            const uint4* hin = g_halo + (((layer * 16 + mb - 1) * 8 + hg) * 2 + wg) * 168;
            uint32_t hv[22] = {};
            rk[0] = rw[2 * t].y; rk[1] = rw[2 * t + 1].y;
            if (mb > 0) {
#pragma unroll 1
                for (int it = 0; it < SPIN_MAX; it++) {
#pragma unroll
                    for (int k = 0; k < 20; k += 4)
                        asm volatile("ld.relaxed.gpu.global.v4.u32 {%0,%1,%2,%3}, [%4];" : "=r"(hv[k]), "=r"(hv[k + 1]), "=r"(hv[k + 2]), "=r"(hv[k + 3]) : "l"(hin + 8 * k + lane) : "memory");
                    asm volatile("ld.relaxed.gpu.global.v2.u32 {%0,%1}, [%2];" : "=r"(hv[20]), "=r"(hv[21]) : "l"(reinterpret_cast<const uint2*>(hin + 160) + t) : "memory");
                    uint32_t m = max(hv[20], hv[21]);
#pragma unroll
                    for (int k = 0; k < 20; k += 2) m = __vimax3_u32(m, hv[k], hv[k + 1]);
                    if (!__any_sync(~0u, m == ~0u)) break;
                }
            }
            if (tid == 0) mbar_arrive(bars + 144);
            if (lane == 0) DBGC(52 - 16 * wg);
#pragma unroll
            for (int j = 0; j < 10; j++) {
                kp[j] = hv[j];
                asm volatile("movmatrix.sync.aligned.m8n8.trans.b16 %0, %1;" : "=r"(vp[j]) : "r"(hv[10 + j]));
            }
            if (up0) rk[0] = __uint_as_float(hv[20]);
            if (up1) rk[1] = __uint_as_float(hv[21]);
        };
        rk[2] = rw[2 * t + (up0 ? 0 : 8)].y; rk[3] = rw[2 * t + 1 + (up1 ? 0 : 8)].y;
        uint32_t qs[4][2];
#pragma unroll
        for (int h = 0; h < 4; h++) {
            qs[h][0] = (t >> 1) == (h & 1) ? f[0][5 * (h >> 1) + 2] : 0u; qs[h][1] = (t >> 1) == (h & 1) ? f[1][5 * (h >> 1) + 2] : 0u;
            asm volatile("" : "+r"(qs[h][0]), "+r"(qs[h][1]));
        }
#pragma unroll
        for (int j = 0; j < 10; j++) asm volatile("" : "+r"(f[0][j]), "+r"(f[1][j]), "+r"(f[0][10 + j]));
        if (warp & 3) above(); else if (wg) halo();
        TSTAMP1T(10, 64);
        float sc[4][3][4];
#pragma unroll
        for (int h = 0; h < 4; h++) {
            const int jb = 5 * (h >> 1) + 3 * (h & 1), js = 5 * (h >> 1) + 2;
#pragma unroll
            for (int nt = 1; nt < 3; nt++) {
#pragma unroll
                for (int e = 0; e < 4; e++) sc[h][nt][e] = 0.f;
                mma_bf16(sc[h][nt], f[0][jb], f[1][jb], f[0][jb + 1], f[1][jb + 1], f[nt - 1][10 + jb], f[nt - 1][11 + jb]);
                mma_bf16_k8(sc[h][nt], qs[h][0], qs[h][1], f[nt - 1][10 + js]);
            }
        }
        if (tid == 128) mbar_arrive(bars + 240);
        if (warp == 0) halo();
        TSTAMP1(8);
#pragma unroll
        for (int h = 0; h < 4; h++) {
            const int jb = 5 * (h >> 1) + 3 * (h & 1), js = 5 * (h >> 1) + 2;
#pragma unroll
            for (int e = 0; e < 4; e++) sc[h][0][e] = 0.f;
            mma_bf16(sc[h][0], f[0][jb], f[1][jb], f[0][jb + 1], f[1][jb + 1], kp[jb], kp[jb + 1]);
            mma_bf16_k8(sc[h][0], qs[h][0], qs[h][1], kp[js]);
        }
        if (warp > 4) { __syncwarp(); if (lane == 0) mbar_arrive(bars + 240); }
        TSTAMP1T(3, 64);
        float p[4][4], sum[4][2];
        uint32_t lg[4][2], mx[4];
        const float rl[4] = {rk[0] * ra, rk[1] * ra, rk[2] * rb, rk[3] * rb};
        auto max2 = [](uint32_t a, uint32_t b) { uint32_t r; asm("max.bf16x2 %0, %1, %2;" : "=r"(r) : "r"(a), "r"(b)); return r; };
#pragma unroll
        for (int h = 0; h < 4; h++) {
            lg[h][0] = pack2((up0 ? sc[h][0][0] : sc[h][1][0]) * rl[0], (up0 ? sc[h][1][2] : sc[h][2][2]) * rl[2]);
            lg[h][1] = pack2((up1 ? sc[h][0][1] : sc[h][1][1]) * rl[1], (up1 ? sc[h][1][3] : sc[h][2][3]) * rl[3]);
            if (edge) {
                if (up0) lg[h][0] = __byte_perm(lg[h][0], 0xce6eu, 0x3254);
                if (up1) lg[h][1] = __byte_perm(lg[h][1], 0xce6eu, 0x3254);
            }
            mx[h] = max2(lg[h][0], lg[h][1]);
        }
#pragma unroll
        for (int o = 1; o <= 2; o <<= 1)
#pragma unroll
            for (int h = 0; h < 4; h++) mx[h] = max2(mx[h], __shfl_xor_sync(~0u, mx[h], o));
#pragma unroll
        for (int h = 0; h < 4; h++)
#pragma unroll
            for (int r = 0; r < 2; r++) {
                const float m = __uint_as_float(r ? mx[h] & 0xffff0000u : mx[h] << 16);
#pragma unroll
                for (int e = 0; e < 2; e++)
                    asm("ex2.approx.ftz.f32 %0, %1;" : "=f"(p[h][2 * r + e]) : "f"((__uint_as_float(r ? lg[h][e] & 0xffff0000u : lg[h][e] << 16) - m) * 1.4426950408889634f));
                sum[h][r] = p[h][2 * r] + p[h][2 * r + 1];
            }
#pragma unroll
        for (int o = 1; o <= 2; o <<= 1)
#pragma unroll
            for (int h = 0; h < 4; h++)
#pragma unroll
                for (int r = 0; r < 2; r++) sum[h][r] += __shfl_xor_sync(~0u, sum[h][r], o);
        TSTAMP1T(5, 64);
        const uint32_t mu = (up0 ? 0xffffu : 0u) | (up1 ? 0xffff0000u : 0u);
        uint32_t ob[10][2];
#pragma unroll
        for (int P = 0; P < 2; P++) {
            float os[2][4];
#pragma unroll
            for (int e = 0; e < 2; e++) {
                const int h = 2 * P + e;
                const float i0 = rcp_apx(sum[h][0]), i1 = rcp_apx(sum[h][1]);
                const uint32_t w0 = pack2(p[h][0] * rk[0] * i0, p[h][1] * rk[1] * i0), w1 = pack2(p[h][2] * rk[2] * i1, p[h][3] * rk[3] * i1);
#pragma unroll
                for (int dt = 0; dt < 3; dt++) {
                    const int j = 5 * P + (dt < 2 ? 3 * e + dt : 2);
                    float o[4] = {0.f, 0.f, 0.f, 0.f};
                    mma_bf16(o, w0 & ~mu, w1 & mu, 0u, w1 & ~mu, vb[j][0], vb[j][1]);
                    mma_bf16_k8(o, w0 & mu, 0u, vp[j]);
                    if (dt < 2) { ob[j][0] = pack2(o[0], o[1]); ob[j][1] = pack2(o[2], o[3]); }
                    else { os[e][0] = o[0]; os[e][1] = o[1]; os[e][2] = o[2]; os[e][3] = o[3]; }
                }
            }
#pragma unroll
            for (int k = 0; k < 4; k++) os[0][k] = t < 2 ? os[0][k] : os[1][k];
            ob[5 * P + 2][0] = pack2(os[0][0], os[0][1]); ob[5 * P + 2][1] = pack2(os[0][2], os[0][3]);
        }
        const uint32_t sl = sbase + (wg ? A1_SM_A1 : A1_SM_A0);
        const uint32_t o0 = (warp & 3) * 2048 + g * 64 + ((t ^ (g >> 1)) << 4), o1 = 8192 + (warp & 3) * 512 + g * 32 + ((t ^ ((g >> 2) << 1)) << 3);
        mbar_wait(bar_done, 0);
        if (wg == 0) mbar_wait(bar_kvf, 0);
#pragma unroll
        for (int h = 0; h < 2; h++) {
            asm volatile("st.shared.v4.u32 [%0], {%1,%2,%3,%4};" ::"r"(sl + o0 + h * 1024), "r"(ob[0][h]), "r"(ob[1][h]), "r"(ob[2][h]), "r"(ob[3][h]) : "memory");
            asm volatile("st.shared.v4.u32 [%0], {%1,%2,%3,%4};" ::"r"(sl + o0 + h * 1024 + 512), "r"(ob[4][h]), "r"(ob[5][h]), "r"(ob[6][h]), "r"(ob[7][h]) : "memory");
            asm volatile("st.shared.v2.u32 [%0], {%1,%2};" ::"r"(sl + o1 + h * 256), "r"(ob[8][h]), "r"(ob[9][h]) : "memory");
        }
        fence_async_smem();
        __syncwarp();
        TSTAMP1T(4, 64);
        TSTAMP1(1);
        TSTAMP2(1);
        const unsigned char* ot = reinterpret_cast<const unsigned char*>(of) + mb * 163840 + wg * 10240;
        if (lane == 0) {
            asm volatile("cp.async.bulk.global.shared::cta.bulk_group [%0], [%1], 2048;" ::"l"(ot + hg * 20480 + (warp & 3) * 2048), "r"(sl + (warp & 3) * 2048) : "memory");
            asm volatile("cp.async.bulk.global.shared::cta.bulk_group [%0], [%1], 512;" ::"l"(ot + hg * 20480 + 8192 + (warp & 3) * 512), "r"(sl + 8192 + (warp & 3) * 512) : "memory");
            asm volatile("cp.async.bulk.commit_group;" ::: "memory");
            if (wg == 0) mbar_arrive(bar_pv);
            asm volatile("cp.async.bulk.wait_group 0;" ::: "memory");
            asm volatile(A1_FRED " [%0], 1;" ::"l"(reinterpret_cast<uint32_t*>(rsum + 2 * SEQ) + (((layer * 16 + mb) * 2 + wg) * 8 + hg) * FSTR) : "memory");
            DBGC(4 + warp);
        }
        TSTAMP4(11);
        float ac2[40];
        const uint64_t db0 = make_desc(sbase, 128, 1280, 0), da0 = make_desc(sl, 16, 1024, 2), da1 = make_desc(sl + 8192, 16, 256, 3);
        const uint32_t o7 = wg ? 640 : (A1_SM_W0 - A1_SM_A0) >> 4;
        const uint32_t trow = ((lane & 7) + 8 * (lane >> 4)) * 128 + (((2 * (warp & 3) + ((lane >> 3) & 1)) ^ (lane & 7)) << 4);
        uint32_t xr[10][2];
        mbar_wait(bar_f2 + 64 * wg + 64, 0);
        if (layer == 0) {
#pragma unroll
            for (int j = 0; j < 10; j += 2) ldsm_x4(&xr[j][0], sl + 51200 + (16 * (warp & 3) + (lane & 15)) * 160 + (lane >> 4) * 16 + 16 * j);
        } else {
#pragma unroll
            for (int j = 0; j < 10; j += 2) ldsm_x4_t(&xr[j][0], sl + 51200 + trow + 1024 * j);
        }
        const uint32_t ri = __shfl_sync(~0u, layer * SEQ + (wg * 2 + ((g >> 1) & 1)) * 512 + (mb * 16 + 4 * (warp & 3) + (g >> 2)) * 2 + (g & 1), lane);
        mbar_wait(bar_wo, 0);
        if (wg) mbar_wait(bar_pv, 0);
        if (wg) asm volatile("bar.sync 2, 128;" ::: "memory"); else asm volatile("bar.sync 1, 128;" ::: "memory");
        TSTAMP2(2);
#pragma unroll
        for (int q = 0; q < 8; q++) {
            uint32_t bo = wo_off(0) >> 4;
            if (q) {
                mbar_wait(bar_f2 + 64 * wg + 8 * q, 0);
                asm volatile("ld.shared.u32 %0, [%1];" : "=r"(bo) : "r"(que + 32 * wg + 4 * q) : "memory");
                bo = __shfl_sync(~0u, bo, 0);
                TSTAMP4(q);
                if (q == 1 && (tid & 127) == 0) DBGC(29 + 8 * wg);
            }
            wgmma_fence();
#pragma unroll
            for (int j = 0; j < 5; j++) wgmma_n80(ac2, (j < 4 ? da0 : da1) + (q == 7 ? o7 : 0u) + (uint64_t)((q < 6 ? q * 640 : 0) + (j & 2) * 16 + (j & 1) * 2), db0 + bo + (uint64_t)(16 * j), j || q);
            wgmma_commit();
            if (q == 0) {
                wgmma_wait<0>();
                if ((tid & 127) == 0) { mbar_arrive(bar_e2 + 16 * wg); mbar_arrive(bar_e2 + 8); }
            }
            if (q == 2 && wg) {
                wgmma_wait<1>();
                if (tid == 128) mbar_arrive(bar_e2 + 24);
            }
        }
        if ((tid & 127) == 0) DBGC(28 + wg * 8 + 7);
        TSTAMP2(3);
        wgmma_wait<0>();
        TSTAMP2(4);
        if (__any_sync(~0u, ac2[0] != ac2[0] || ac2[2] != ac2[2])) {
#pragma unroll
            for (int i = 0; i < 40; i++) ac2[i] = 0.f;
            uint32_t a[20], an[20];
            auto lda = [&](uint32_t (&r)[20], int h) {
#pragma unroll
                for (int u = 0; u < 4; u++)
                    asm volatile("ld.relaxed.gpu.global.v4.u32 {%0,%1,%2,%3}, [%4];" : "=r"(r[4 * u]), "=r"(r[4 * u + 1]), "=r"(r[4 * u + 2]), "=r"(r[4 * u + 3]) : "l"(ot + h * 20480 + o0 + u * 512) : "memory");
#pragma unroll
                for (int u = 0; u < 2; u++)
                    asm volatile("ld.relaxed.gpu.global.v2.u32 {%0,%1}, [%2];" : "=r"(r[16 + 2 * u]), "=r"(r[17 + 2 * u]) : "l"(ot + h * 20480 + o1 + u * 256) : "memory");
            };
            lda(an, 0);
#pragma unroll 1
            for (int h = 0; h < 8; h++) {
#pragma unroll 1
                for (int it = 0; it < SPIN_MAX; it++) {
                    uint32_t m = 0;
#pragma unroll
                    for (int k = 0; k < 20; k += 2) m = __vimax3_u32(m, an[k], an[k + 1]);
                    if (!__any_sync(~0u, m == ~0u)) break;
                    lda(an, h);
                }
#pragma unroll
                for (int k = 0; k < 20; k++) a[k] = an[k];
                lda(an, min(h + 1, 7));
                const unsigned char* bp = (h == hg ? wo + hg * 8 * WOB : stg + wo_off(h + (h < hg))) + g * 16;
#pragma unroll
                for (int n = 0; n < 10; n++) {
                    const uint4 b0 = *reinterpret_cast<const uint4*>(bp + 1280 * n + t * 128), b1 = *reinterpret_cast<const uint4*>(bp + 1280 * n + 512 + t * 128);
                    const uint2 b2 = *reinterpret_cast<const uint2*>(bp + 1280 * n + 1024 + (t >> 1) * 128 + (t & 1) * 8);
                    mma_bf16(ac2 + 4 * n, a[0], a[8], a[1], a[9], b0.x, b0.y); mma_bf16(ac2 + 4 * n, a[2], a[10], a[3], a[11], b0.z, b0.w);
                    mma_bf16(ac2 + 4 * n, a[4], a[12], a[5], a[13], b1.x, b1.y); mma_bf16(ac2 + 4 * n, a[6], a[14], a[7], a[15], b1.z, b1.w);
                    mma_bf16(ac2 + 4 * n, a[16], a[18], a[17], a[19], b2.x, b2.y);
                }
            }
        }
#pragma unroll
        for (int j = 0; j < 10; j++)
#pragma unroll
            for (int hh = 0; hh < 2; hh++) {
                const uint32_t a = pack2(ac2[4 * j + 2 * hh], ac2[4 * j + 2 * hh + 1]);
                const __nv_bfloat162 r = __hadd2_rn(*reinterpret_cast<const __nv_bfloat162*>(&xr[j][hh]), *reinterpret_cast<const __nv_bfloat162*>(&a));
                xr[j][hh] = *reinterpret_cast<const uint32_t*>(&r);
            }
        const uint32_t so = sl + 30720;
#pragma unroll
        for (int j = 0; j < 10; j += 2) stsm_x4_t(so + trow + 1024 * j, xr[j][0], xr[j][1], xr[j + 1][0], xr[j + 1][1]);
        fence_async_smem();
        if (wg) asm volatile("bar.sync 2, 128;" ::: "memory"); else asm volatile("bar.sync 1, 128;" ::: "memory");
        TSTAMP2(5);
        if ((tid & 127) == 0) {
            asm volatile("cp.async.bulk.tensor.2d.global.shared::cta.bulk_group [%0, {%1, %2}], [%3];" ::"l"(&tmX1), "r"(mb * 128 + 64 * wg), "r"(hg * 80), "r"(so) : "memory");
            asm volatile("cp.async.bulk.commit_group;" ::: "memory");
        }
        __syncwarp();
        const float p0 = *(volatile const float*)&rw[g].x, p1 = *(volatile const float*)&rw[g + 8].x;
        float s[3][4] = {};
        const uint32_t pp[2] = {__byte_perm(__float_as_uint(p0), 0, 0x3232), __byte_perm(__float_as_uint(p1), 0, 0x3232)};
#pragma unroll
        for (int j = 0; j < 10; j += 2) {
            const uint32_t d0 = sub2(xr[j][0], pp[0]), d1 = sub2(xr[j][1], pp[1]), d2 = sub2(xr[j + 1][0], pp[0]), d3 = sub2(xr[j + 1][1], pp[1]);
            mma_bf16(s[0], xr[j][0], xr[j][1], xr[j + 1][0], xr[j + 1][1], 0x3f803f80u, 0x3f803f80u);
            mma_bf16(s[1], d0, d1, d2, d3, d0, d2);
            mma_bf16(s[2], d0, d1, d2, d3, d1, d3);
        }
        if (t == (g >> 1)) {
            float2* rp = rsum + ri;
            asm volatile("red.relaxed.gpu.global.add.v2.f32 [%0], {%1, %2};" ::"l"(rp), "f"(fmaf(-80.f, p0, s[0][0])), "f"((g & 1) ? s[1][1] : s[1][0]) : "memory");
            asm volatile("red.relaxed.gpu.global.add.v2.f32 [%0], {%1, %2};" ::"l"(rp + 4), "f"(fmaf(-80.f, p1, s[0][2])), "f"((g & 1) ? s[2][3] : s[2][2]) : "memory");
        }
        asm volatile("cp.async.bulk.wait_group.read 0;" ::: "memory");
        TSTAMP2(6);
        if (tid == 0) DBGC(63);
        if (tid == 128) DBGC(28);
        if (tid == 0) DBGCAL(2);
        GSTAMP(g_tim1, 14);
        SPAN(1 + 4 * layer, 3);
    }
}

static int h_nsm;
static void* h_sym[11];
static TileTab h_tab;
static CUtensorMap h_tmX0, h_tmX1, h_tmR0, h_tmR1, h_tmX1st, h_tmOut, h_tmWq, h_tmWo;
typedef CUresult (*PFN_encodeTiled)(CUtensorMap*, CUtensorMapDataType, cuuint32_t, void*, const cuuint64_t*, const cuuint64_t*,
                                    const cuuint32_t*, const cuuint32_t*, CUtensorMapInterleave, CUtensorMapSwizzle,
                                    CUtensorMapL2promotion, CUtensorMapFloatOOBfill);
static void make_tmap(CUtensorMap* tm, const void* ptr, uint64_t cols, uint64_t rows, uint32_t bc, uint32_t br, CUtensorMapSwizzle sw, uint64_t pitch = 0, uint64_t hi = 0, uint32_t bh = 2) {
    static PFN_encodeTiled fn = nullptr;
    if (!fn) {
        void* p = nullptr; cudaDriverEntryPointQueryResult qr;
        cudaGetDriverEntryPoint("cuTensorMapEncodeTiled", &p, cudaEnableDefault, &qr);
        fn = (PFN_encodeTiled)p;
    }
    if (br == 0) {
        cuuint64_t dims[4] = {cols, 2, rows / 8, 4}; cuuint64_t strides[3] = {cols * 2, cols * 16, cols * 4};
        cuuint32_t box[4] = {bc, 2, 8, 4}; cuuint32_t es[4] = {1, 1, 1, 1};
        fn(tm, CU_TENSOR_MAP_DATA_TYPE_BFLOAT16, 4, const_cast<void*>(ptr), dims, strides, box, es, CU_TENSOR_MAP_INTERLEAVE_NONE, sw,
           CU_TENSOR_MAP_L2_PROMOTION_L2_128B, CU_TENSOR_MAP_FLOAT_OOB_FILL_NONE);
        return;
    }
    if (bh == 5) {
        cuuint64_t dims[5] = {64, 64, 2, 16, 10}; cuuint64_t strides[4] = {pitch * 2, hi * 2, cols * 2, rows * 2};
        cuuint32_t box[5] = {64, 64, 2, 1, 1}; cuuint32_t es[5] = {1, 1, 1, 1, 1};
        fn(tm, CU_TENSOR_MAP_DATA_TYPE_BFLOAT16, 5, const_cast<void*>(ptr), dims, strides, box, es, CU_TENSOR_MAP_INTERLEAVE_NONE, sw,
           CU_TENSOR_MAP_L2_PROMOTION_L2_128B, CU_TENSOR_MAP_FLOAT_OOB_FILL_NONE);
        return;
    }
    if (hi) {
        cuuint64_t dims[3] = {cols, rows, hi == 64 ? 32u : 2u}; cuuint64_t strides[2] = {pitch * 2, hi * 2};
        cuuint32_t box[3] = {bc, br, bh}; cuuint32_t es[3] = {1, 1, 1};
        fn(tm, CU_TENSOR_MAP_DATA_TYPE_BFLOAT16, 3, const_cast<void*>(ptr), dims, strides, box, es, CU_TENSOR_MAP_INTERLEAVE_NONE, sw,
           CU_TENSOR_MAP_L2_PROMOTION_L2_128B, CU_TENSOR_MAP_FLOAT_OOB_FILL_NONE);
        return;
    }
    cuuint64_t dims[2] = {cols, rows}; cuuint64_t strides[1] = {(pitch ? pitch : cols) * 2};
    cuuint32_t box[2] = {bc, br}; cuuint32_t es[2] = {1, 1};
    fn(tm, CU_TENSOR_MAP_DATA_TYPE_BFLOAT16, 2, const_cast<void*>(ptr), dims, strides, box, es, CU_TENSOR_MAP_INTERLEAVE_NONE, sw,
       CU_TENSOR_MAP_L2_PROMOTION_L2_128B, CU_TENSOR_MAP_FLOAT_OOB_FILL_NONE);
}
template <typename... Args>
static void launch_pdl(void (*kern)(Args...), int grid, int block, int smem, Args... args) {
    cudaLaunchConfig_t cfg = {};
    cfg.gridDim = dim3(grid); cfg.blockDim = dim3(block); cfg.dynamicSmemBytes = smem; cfg.stream = cudaStreamPerThread;
    cudaLaunchAttribute at[1];
    at[0].id = cudaLaunchAttributeProgrammaticStreamSerialization; at[0].val.programmaticStreamSerializationAllowed = 1;
    cfg.attrs = at; cfg.numAttrs = 1;
    cudaLaunchKernelEx(&cfg, kern, args...);
}
static void launch_stage(int k, void* const* d_in, void* d_out) {
    const KgIn kg = {(const bf16*)d_in[4], (const bf16*)d_in[5], (const bf16*)d_in[6], (const bf16*)d_in[7], (const bf16*)d_in[8], (const bf16*)d_in[0], (const bf16*)d_in[1], (const bf16*)d_in[2],
                      (uint4*)h_sym[0], (uint4*)h_sym[1], (uint4*)h_sym[2], (uint4*)h_sym[3], (uint4*)h_sym[4], (float*)h_sym[5]};
    switch (k) {
        case 0: kgen_kernel<<<DM, KG_THREADS, 0, cudaStreamPerThread>>>(kg, h_tmWq, h_tmWo); break;
        case 1: launch_pdl(a1_kernel, h_nsm, A1_THREADS, A1_SMEM, 0, (const bf16*)d_in[0], (const unsigned char*)h_sym[1], (const unsigned char*)h_sym[2], (float2*)h_sym[4], (uint4*)h_sym[6], h_tmX0, h_tmR0, h_tmX1st, h_tab); break;
        case 3: launch_pdl(conv_kernel, DM / CV_CPB, CV_THREADS, CV_SMEM, (const bf16*)d_in[9], 0, (const uint4*)h_sym[7], (const float4*)h_sym[4], (const bf16*)h_sym[8], (bf16*)h_sym[9], (const uint4*)h_sym[0], (bf16*)h_sym[10], h_tmOut); break;
        case 5: launch_pdl(a1_kernel, h_nsm, A1_THREADS, A1_SMEM, 1, (const bf16*)d_in[0], (const unsigned char*)h_sym[1], (const unsigned char*)h_sym[2], (float2*)h_sym[4], (uint4*)h_sym[6], h_tmX1, h_tmR1, h_tmX1st, h_tab); break;
        case 7: launch_pdl(conv_kernel, DM / CV_CPB, CV_THREADS, CV_SMEM, (const bf16*)d_in[9], 1, (const uint4*)h_sym[7] + SEQ / 8, (const float4*)h_sym[4] + SEQ / 2, (const bf16*)h_sym[8], (bf16*)h_sym[10], (const uint4*)h_sym[0], (bf16*)h_sym[10], h_tmOut); break;
        default: break;
    }
}
static int n_stage_kernels() { return 9; }
static const char* stage_name(int k) { const char* n[] = {"kgen", "a1", "a2", "conv", "tr", "a1", "a2", "conv", "tr"}; return n[k]; }

extern "C" void kernel_launch(void* const* d_in, const int* in_sizes, int n_in, void* d_out, int out_size) {
    (void)in_sizes; (void)n_in; (void)out_size;
    static const void *p_in = nullptr, *p_w1 = nullptr, *p_w2 = nullptr, *p_out = nullptr;
    if (p_in != d_in[0] || p_w1 != d_in[1] || p_w2 != d_in[2] || p_out != d_out) {
        cudaFuncSetAttribute(conv_kernel, cudaFuncAttributeMaxDynamicSharedMemorySize, CV_SMEM);
        cudaFuncSetAttribute(kgen_kernel, cudaFuncAttributePreferredSharedMemoryCarveout, 100);
        cudaFuncSetAttribute(a1_kernel, cudaFuncAttributeMaxDynamicSharedMemorySize, A1_SMEM);
        int dev; cudaGetDevice(&dev); cudaDeviceGetAttribute(&h_nsm, cudaDevAttrMultiProcessorCount, dev);
        if (h_nsm != 132) h_nsm = 128;
        h_tab.ns = h_nsm == 132 ? 132 : ~0u;
        for (int i = 0; i < 264; i++) {
            const int h = (i - 64) >> 1;
            const int t = i >= 132 ? i - 132 : i < 64 ? ((i >> 1) & 7) * 16 + (i >> 4) * 2 + (i & 1) : i < 120 ? (1 + h % 7) * 16 + 8 + (h / 7) * 2 + (i & 1) : i < 124 ? 128 : i - 116;
            const int hg = (4 * (t >> 6) + (t & 3)) & 7;
            h_tab.e[i] = {(unsigned char)((t >> 2) & 15), (unsigned char)hg, (unsigned char)(5 * (hg >> 2)), (unsigned char)t, (uint32_t)(hg * 10 * WQ_STAGE)};
        }
        cudaGetSymbolAddress(&h_sym[0], g_tap); cudaGetSymbolAddress(&h_sym[1], g_wq); cudaGetSymbolAddress(&h_sym[2], g_wo);
        cudaGetSymbolAddress(&h_sym[3], g_halo); cudaGetSymbolAddress(&h_sym[4], g_sum); cudaGetSymbolAddress(&h_sym[5], g_csp); cudaGetSymbolAddress(&h_sym[6], g_of);
        cudaGetSymbolAddress(&h_sym[7], g_piv); cudaGetSymbolAddress(&h_sym[8], g_x1T); cudaGetSymbolAddress(&h_sym[9], g_xcT); cudaGetSymbolAddress(&h_sym[10], g_yT);
        void *px1, *px2;
        cudaGetSymbolAddress(&px1, g_x1T); cudaGetSymbolAddress(&px2, g_xcT);
        make_tmap(&h_tmX0, d_in[0], 128 * 640, 64, 64, 64, CU_TENSOR_MAP_SWIZZLE_128B, 1280, 640, 5);
        make_tmap(&h_tmX1, px2, 128, 64 * XCP, 64, 64, CU_TENSOR_MAP_SWIZZLE_128B, XCP, 64, 5);
        make_tmap(&h_tmR0, d_in[0], 640, 1024, 80, 64, CU_TENSOR_MAP_SWIZZLE_NONE, 1280, 640, 1);
        make_tmap(&h_tmR1, px2, 64, 640, 64, 80, CU_TENSOR_MAP_SWIZZLE_128B, XCP, 64, 1);
        make_tmap(&h_tmX1st, px1, 2048, 640, 64, 80, CU_TENSOR_MAP_SWIZZLE_128B, XCP);
        make_tmap(&h_tmWq, d_in[1], 1920, 640, 32, 0, CU_TENSOR_MAP_SWIZZLE_64B);
        make_tmap(&h_tmWo, d_in[2], 640, 640, 32, 80, CU_TENSOR_MAP_SWIZZLE_64B);
        make_tmap(&h_tmOut, d_out, 640, 2048, 80, 8, CU_TENSOR_MAP_SWIZZLE_NONE);
        p_in = d_in[0]; p_w1 = d_in[1]; p_w2 = d_in[2]; p_out = d_out;
    }
    for (int k = 0; k < n_stage_kernels(); k++) launch_stage(k, d_in, d_out);
}
```

```cpp
#include <cuda_runtime.h>
#include <cuda_bf16.h>
#include <stdint.h>
#include <cuda.h>

typedef __nv_bfloat16 bf16;

constexpr int SEQ = 2048;
constexpr int DM = 640;
constexpr int NMODE = 192;

__device__ __forceinline__ float bf2f(bf16 v) { return __bfloat162float(v); }
__device__ __forceinline__ float rbf(float v) {
    uint32_t r;
    asm("cvt.rn.bf16x2.f32 %0, %1, %2;" : "=r"(r) : "f"(v), "f"(0.f));
    return __uint_as_float(r);
}
__device__ __forceinline__ uint32_t pack2(float lo, float hi) {
    __nv_bfloat162 t = __floats2bfloat162_rn(lo, hi);
    return *reinterpret_cast<uint32_t*>(&t);
}
__device__ __forceinline__ void pdl_sync() {
    asm volatile("griddepcontrol.wait;" ::: "memory");
    asm volatile("griddepcontrol.launch_dependents;" ::: "memory");
}
__device__ __forceinline__ float sqrt_apx(float v) { float r; asm("sqrt.approx.ftz.f32 %0, %1;" : "=f"(r) : "f"(v)); return r; }
__device__ __forceinline__ float rcp_apx(float v) { float r; asm("rcp.approx.ftz.f32 %0, %1;" : "=f"(r) : "f"(v)); return r; }
__device__ __forceinline__ uint32_t smem_u32(const void* p) { return (uint32_t)__cvta_generic_to_shared(p); }

constexpr int TPAD = 16;
constexpr int DLEN = 544;
constexpr int TAP_W2 = DLEN * 8, TAP_W3 = TAP_W2 + 768, TAP_C = TAP_W3 + 768, TAPB = TAP_C + 384;
__device__ __align__(128) uint4 g_tap[DM * 128];
#define XPAD 64
constexpr int XCP = SEQ + XPAD;
__device__ __align__(128) bf16 g_x1T[DM * XCP];
__device__ __align__(128) bf16 g_xcT[DM * XCP];
__device__ __align__(128) uint4 g_of[128 * 1280];
constexpr int WQ_STAGE = 240 * 128, WOB = 80 * 160;
__device__ __align__(128) uint4 g_wq[8 * 10 * WQ_STAGE / 16];
__device__ __align__(128) uint4 g_wo[64 * WOB / 16];
__device__ __align__(16) float g_csp[10 * 1920];
#define FSTR 32
__device__ __align__(128) float2 g_sum[2 * SEQ + 256 * FSTR];
__device__ __align__(16) bf16 g_piv[2 * SEQ];
__device__ __align__(128) bf16 g_yT[DM * XCP];
__device__ uint32_t g_epoch;
__device__ __align__(16) unsigned long long g_rstat[SEQ];
__device__ __align__(128) uint4 g_halo[640 * 148];
__device__ __forceinline__ unsigned long long tagw(uint32_t payload, uint32_t tag) { return ((unsigned long long)tag << 32) | payload; }
__device__ __forceinline__ ulonglong2 ld_tag2(const ulonglong2* p) {
    ulonglong2 v;
    asm volatile("ld.relaxed.gpu.global.v2.u64 {%0, %1}, [%2];" : "=l"(v.x), "=l"(v.y) : "l"(p) : "memory");
    return v;
}
__device__ __forceinline__ bool tag_ok(ulonglong2 v, uint32_t tag) { return (uint32_t)(v.x >> 32) == tag && (uint32_t)(v.y >> 32) == tag; }
__device__ __forceinline__ uint32_t ld_epoch() { uint32_t v; asm volatile("ld.relaxed.gpu.global.u32 %0, [%1];" : "=r"(v) : "l"(&g_epoch) : "memory"); return v + 1; }
constexpr int SPIN_MAX = 1 << 20;
__device__ uint32_t g_started[4];
__device__ __forceinline__ void sm_started(int slot) { asm volatile("red.relaxed.gpu.global.add.u32 [%0], 1;" ::"l"(g_started + slot) : "memory"); }
__device__ __noinline__ void sm_idle(int slot) {
    if (threadIdx.x) return;
    sm_started(slot);
    const uint32_t want = ld_epoch() * gridDim.x;
    pdl_sync();
#pragma unroll 1
    for (int it = 0; it < SPIN_MAX; it++) {
        uint32_t v;
        asm volatile("ld.relaxed.gpu.global.u32 %0, [%1];" : "=r"(v) : "l"(g_started + slot) : "memory");
        if ((int)(v - want) >= 0) break;
        __nanosleep(100);
    }
}
struct TileTab { uint32_t ns, pad; struct { unsigned char mb, hg, kb0, tile; uint32_t woff; } __align__(8) e[264]; };
__device__ __forceinline__ bool elect() {
    uint32_t p;
    asm volatile("{\n.reg .pred p;\nelect.sync _|p, 0xffffffff;\nselp.b32 %0, 1, 0, p;\n}" : "=r"(p));
    return p;
}
#define DBG_SYMS
#define TSTAMP(i)
#define TSTAMP1(i)
#define TSTAMP1T(i, t)
#define TSTAMP1X(i, t)
#define SPAN(k, i)
#define GSTAMP(arr, i)
#define TSTAMP2(i)
#define TSTAMP3(i)
#define TSTAMP4(i)
#define TSTAMPK(i, t)
#define DBGC(i)
#define DBGV(i, v)
#define DBGCAL(i)

__device__ __forceinline__ void mma_bf16(float* d, uint32_t a0, uint32_t a1, uint32_t a2, uint32_t a3, uint32_t b0, uint32_t b1) {
    asm volatile("mma.sync.aligned.m16n8k16.row.col.f32.bf16.bf16.f32 {%0,%1,%2,%3}, {%4,%5,%6,%7}, {%8,%9}, {%0,%1,%2,%3};"
                 : "+f"(d[0]), "+f"(d[1]), "+f"(d[2]), "+f"(d[3]) : "r"(a0), "r"(a1), "r"(a2), "r"(a3), "r"(b0), "r"(b1));
}
__device__ __forceinline__ void mma_bf16_k8(float* d, uint32_t a0, uint32_t a1, uint32_t b0) {
    asm volatile("mma.sync.aligned.m16n8k8.row.col.f32.bf16.bf16.f32 {%0,%1,%2,%3}, {%4,%5}, {%6}, {%0,%1,%2,%3};"
                 : "+f"(d[0]), "+f"(d[1]), "+f"(d[2]), "+f"(d[3]) : "r"(a0), "r"(a1), "r"(b0));
}
__device__ __forceinline__ void ldsm_x4(uint32_t* r, uint32_t addr) {
    asm volatile("ldmatrix.sync.aligned.m8n8.x4.shared.b16 {%0,%1,%2,%3}, [%4];"
                 : "=r"(r[0]), "=r"(r[1]), "=r"(r[2]), "=r"(r[3]) : "r"(addr));
}

__device__ __forceinline__ void ldsm_x4_t(uint32_t* r, uint32_t addr) {
    asm volatile("ldmatrix.sync.aligned.m8n8.x4.trans.shared.b16 {%0,%1,%2,%3}, [%4];"
                 : "=r"(r[0]), "=r"(r[1]), "=r"(r[2]), "=r"(r[3]) : "r"(addr));
}
__device__ __forceinline__ void mbar_init(uint32_t bar, int count) { asm volatile("mbarrier.init.shared::cta.b64 [%0], %1;" ::"r"(bar), "r"(count)); }
__device__ __forceinline__ void mbar_arrive(uint32_t bar) { asm volatile("mbarrier.arrive.shared::cta.b64 _, [%0];" ::"r"(bar) : "memory"); }
__device__ __forceinline__ void mbar_wait(uint32_t bar, uint32_t parity) {
    asm volatile("{\n.reg .pred p;\nWAIT_LOOP:\n"
                 "mbarrier.try_wait.parity.shared::cta.b64 p, [%0], %1;\n"
                 "@p bra.uni WAIT_DONE;\nbra.uni WAIT_LOOP;\nWAIT_DONE:\n}" ::"r"(bar), "r"(parity) : "memory");
}

__device__ __forceinline__ void mbar_expect_tx(uint32_t bar, uint32_t bytes) {
    asm volatile("mbarrier.arrive.expect_tx.shared::cta.b64 _, [%0], %1;" ::"r"(bar), "r"(bytes) : "memory");
}
__device__ __forceinline__ void tma_load_2d(uint32_t dst, const void* tmap, int c0, int c1, uint32_t bar) {
    asm volatile("cp.async.bulk.tensor.2d.shared::cluster.global.mbarrier::complete_tx::bytes [%0], [%1, {%3, %4}], [%2];"
                 ::"r"(dst), "l"(tmap), "r"(bar), "r"(c0), "r"(c1) : "memory");
}
__device__ __forceinline__ void tma_load_3d(uint32_t dst, const void* tmap, int c0, int c1, int c2, uint32_t bar) {
    asm volatile("cp.async.bulk.tensor.3d.shared::cluster.global.mbarrier::complete_tx::bytes [%0], [%1, {%3, %4, %5}], [%2];"
                 ::"r"(dst), "l"(tmap), "r"(bar), "r"(c0), "r"(c1), "r"(c2) : "memory");
}
__device__ __forceinline__ void fence_async_smem() { asm volatile("fence.proxy.async.shared::cta;" ::: "memory"); }
__device__ __forceinline__ void bulk_load(uint32_t dst, const void* src, uint32_t bytes, uint32_t bar) {
    asm volatile("cp.async.bulk.shared::cluster.global.mbarrier::complete_tx::bytes [%0], [%1], %2, [%3];"
                 ::"r"(dst), "l"(src), "r"(bytes), "r"(bar) : "memory");
}
__device__ __forceinline__ void tma_store_2d(const void* tmap, int c0, int c1, uint32_t src) {
    asm volatile("cp.async.bulk.tensor.2d.global.shared::cta.bulk_group [%0, {%1, %2}], [%3];" ::"l"(tmap), "r"(c0), "r"(c1), "r"(src) : "memory");
    asm volatile("cp.async.bulk.commit_group;" ::: "memory");
    asm volatile("cp.async.bulk.wait_group.read 0;" ::: "memory");
}
__device__ __forceinline__ void stsm_x4(uint32_t addr, uint32_t r0, uint32_t r1, uint32_t r2, uint32_t r3) {
    asm volatile("stmatrix.sync.aligned.m8n8.x4.shared.b16 [%0], {%1,%2,%3,%4};" ::"r"(addr), "r"(r0), "r"(r1), "r"(r2), "r"(r3) : "memory");
}
__device__ __forceinline__ void stsm_x4_t(uint32_t addr, uint32_t r0, uint32_t r1, uint32_t r2, uint32_t r3) {
    asm volatile("stmatrix.sync.aligned.m8n8.x4.trans.shared.b16 [%0], {%1,%2,%3,%4};" ::"r"(addr), "r"(r0), "r"(r1), "r"(r2), "r"(r3) : "memory");
}
__device__ __forceinline__ void prefetch_tmap(const void* tmap) { asm volatile("prefetch.tensormap [%0];" ::"l"(tmap) : "memory"); }

__device__ __forceinline__ float2 cexp_at(float wr2, float wi, float p) {
    float er;
    asm("ex2.approx.ftz.f32 %0, %1;" : "=f"(er) : "f"(wr2 * p));
    float th = wi * p;
    const float k = rintf(th * 0.15915494309189535f);
    th = fmaf(k, -6.2831854820251465f, th);
    th = fmaf(k, 1.7484555314695172e-7f, th);
    return make_float2(er * __cosf(th), er * __sinf(th));
}
__device__ __forceinline__ float2 cmul(float2 a, float2 b) {
    return make_float2(fmaf(a.x, b.x, -a.y * b.y), fmaf(a.x, b.y, a.y * b.x));
}
__device__ __forceinline__ float2 csqr(float2 a) { return make_float2(fmaf(a.x, a.x, -a.y * a.y), (a.x + a.x) * a.y); }
__device__ __forceinline__ uint32_t packh(float2 v) {
    uint32_t r;
    asm("cvt.rn.f16x2.f32 %0, %1, %2;" : "=r"(r) : "f"(v.y), "f"(v.x));
    return r;
}
__device__ __forceinline__ void mma_f16(float* d, uint32_t a0, uint32_t a1, uint32_t a2, uint32_t a3, uint32_t b0, uint32_t b1) {
    asm volatile("mma.sync.aligned.m16n8k16.row.col.f32.f16.f16.f32 {%0,%1,%2,%3}, {%4,%5,%6,%7}, {%8,%9}, {%0,%1,%2,%3};"
                 : "+f"(d[0]), "+f"(d[1]), "+f"(d[2]), "+f"(d[3]) : "r"(a0), "r"(a1), "r"(a2), "r"(a3), "r"(b0), "r"(b1));
}

struct KgIn { const bf16 *logA, *Aim, *Cre, *Cim, *logdt, *x, *wqkv, *wo; uint4 *tap, *wq, *wop, *halo, *sum; float* csp; };
constexpr int KG_THREADS = NMODE / 2;

constexpr int KG_SMEM = 15 * 14336 + 3 * 5120 + 192;
__global__ void __launch_bounds__(512, 1) kgen_kernel(const KgIn in, const __grid_constant__ CUtensorMap tmWq, const __grid_constant__ CUtensorMap tmWo,
                                                        const __grid_constant__ CUtensorMap tmWt, const __grid_constant__ CUtensorMap tmWc) {
    extern __shared__ __align__(1024) uint4 tabs[];
#define KG_CS 1
#define KG_ROT 0
    const int lane = threadIdx.x & 31, w16 = (__shfl_sync(~0u, threadIdx.x >> 5, 0) + KG_ROT) & 15, grp = w16 / 3, warp = w16 - 3 * grp;
    const int d = blockIdx.x * 5 + grp, tid = warp * 32 + lane;
    uint4* tab = tabs + grp * (3 * 896);
    SPAN(0, 0); SPAN(0, 1);
    TSTAMPK(0, 0);
    asm volatile("griddepcontrol.launch_dependents;" ::: "memory");
    if (w16 == 15) {
        const uint32_t b0 = smem_u32(tab), wbar = b0 + 3 * 5120;
        const int blk = blockIdx.x, nq = blk < 112 ? 4 : 2, nj = nq + (blk < 64 ? 1 : 2);
        auto fetch = [&](int i) {
            const uint32_t dst = b0 + (i % 3) * 5120, bar = wbar + 8 * i;
            if (i < nq) {
                const int p = blk + 64 * (i & 2), kb = p / 24;
                mbar_expect_tx(bar, 5120);
                tma_load_3d(dst, &tmWq, 0, kb * 64 + (i & 1) * 32, (p - 24 * kb) * 5, bar);
            } else if (i < nj) {
                const int o = i == nq ? blk : 255 - blk;
                mbar_expect_tx(bar, o < 128 ? 5120 : 2560);
                asm volatile("cp.async.bulk.tensor.5d.shared::cluster.global.mbarrier::complete_tx::bytes [%0], [%1, {%3, %3, %4, %3, %5}], [%2];"
                             ::"r"(dst), "l"(o < 128 ? &tmWo : &tmWt), "r"(bar), "r"(0), "r"((o & 7) * 10 + (o >> 6) * 4), "r"(((o >> 3) & 7) * 5) : "memory");
            }
        };
        if (elect()) {
#pragma unroll
            for (int i = 0; i < 6; i++) mbar_init(wbar + 8 * i, 1);
            asm volatile("fence.mbarrier_init.release.cluster;" ::: "memory");
#pragma unroll
            for (int i = 0; i < 3; i++) fetch(i);
            prefetch_tmap(&tmWo); prefetch_tmap(&tmWt); prefetch_tmap(&tmWc);
#pragma unroll 1
            for (int i = 0; i < nj; i++) {
                const int p = blk + 64 * (i & 2), kb = p / 24, hg = p & 7, sec = (p - 24 * kb) >> 3, o = i == nq ? blk : 255 - blk, cg = (o >> 3) & 7, hb = o & 7;
                const unsigned char* dst = i < nq ? reinterpret_cast<unsigned char*>(in.wq) + (hg * 10 + (hg < 4 ? kb : kb < 5 ? kb + 5 : kb - 5)) * WQ_STAGE + ((i & 1) * 3 + sec) * 5120
                                                  : reinterpret_cast<unsigned char*>(in.wop) + (cg * 8 + (hb == cg ? 0 : hb + (hb < cg))) * WOB + (o >> 6) * 5120;
                mbar_wait(wbar + 8 * i, 0);
                if (i == 0) TSTAMPK(2, (15 - KG_ROT) * 32);
                if (i == 3) TSTAMPK(5, (15 - KG_ROT) * 32);
                asm volatile("cp.async.bulk.global.shared::cta.bulk_group [%0], [%1], %2;" ::"l"(dst), "r"(b0 + (i % 3) * 5120), "r"(i < nq || o < 128 ? 5120 : 2560) : "memory");
                asm volatile("cp.async.bulk.commit_group;" ::: "memory");
                if (i == 2) {
                    asm volatile("cp.async.bulk.wait_group.read 0;" ::: "memory");
                    TSTAMPK(3, (15 - KG_ROT) * 32);
#pragma unroll 1
                    for (int k = 3; k < 6; k++) fetch(k);
                }
            }
            asm volatile("cp.async.bulk.wait_group.read 0;" ::: "memory");
        }
        TSTAMPK(11, (15 - KG_ROT) * 32);
        return;
    }
    const bf16 pdt = in.logdt[d];
    const uint32_t pla = reinterpret_cast<const uint32_t*>(in.logA)[d * KG_THREADS + tid], pai = reinterpret_cast<const uint32_t*>(in.Aim)[d * KG_THREADS + tid];
    const uint32_t pcr = reinterpret_cast<const uint32_t*>(in.Cre)[d * KG_THREADS + tid], pci = reinterpret_cast<const uint32_t*>(in.Cim)[d * KG_THREADS + tid];
    const bf16* pfq = tid < 30 ? in.wqkv + (size_t)(d * 30 + tid) * 64 : tid < 40 ? in.wo + (size_t)(d * 10 + tid - 30) * 64 : in.x + (size_t)(d * 32 + tid - 40) * 64;
#define KG_PF 0
    if (tid < (KG_PF == 3 ? 0 : KG_PF ? 40 : 72)) asm volatile("prefetch.global.L2 [%0];" ::"l"(pfq));
    asm volatile("st.global.v4.u32 [%0], {%1,%1,%1,%1};" ::"l"(in.halo + d * 148 + tid), "r"(~0u));
    if (tid < 52) asm volatile("st.global.v4.u32 [%0], {%1,%1,%1,%1};" ::"l"(in.halo + d * 148 + 96 + tid), "r"(~0u));
    else if (w16 == 2) {
        if (lane < 16) in.sum[blockIdx.x * 16 + lane] = make_uint4(0, 0, 0, 0);
        else if (lane < 20) reinterpret_cast<uint32_t*>(in.sum + 2048)[(blockIdx.x * 4 + lane - 16) * FSTR] = 0;
    }
    const uint32_t tw = smem_u32(tab) + warp * 14336, cbar = smem_u32(tabs) + 15 * 14336 + 3 * 5120 + 64 + 8 * w16;
    if (lane == 0) { mbar_init(cbar, 1); mbar_expect_tx(cbar, 2048); }
    const int g = lane >> 2, t = lane & 3;
    const uint32_t sta = tw + lane * 128 + ((2 * (lane & 3) + ((lane >> 2) & 1)) << 4);
    const uint32_t lda = tw + t * 128 + ((g ^ (2 * t)) << 4);
    const uint32_t stb = tw + 12288 + lane * 64 + ((4 * ((lane >> 1) & 1) + ((lane >> 2) & 3)) << 3);
    const uint32_t ldb = tw + 12288 + t * 64 + ((g ^ (4 * (t >> 1))) << 3);
    auto sts4 = [&](int e, int off, uint32_t a, uint32_t b, uint32_t c, uint32_t dd) {
        asm volatile("st.shared.v4.u32 [%0], {%1,%2,%3,%4};" ::"r"((sta ^ (e << 4)) + off), "r"(a), "r"(b), "r"(c), "r"(dd) : "memory");
    };
    auto lds4 = [&](int sp, int off, uint32_t* r) {
        asm volatile("ld.shared.v4.u32 {%0,%1,%2,%3}, [%4];" : "=r"(r[0]), "=r"(r[1]), "=r"(r[2]), "=r"(r[3]) : "r"((lda ^ ((sp & 1) << 4)) + sp * 512 + off) : "memory");
    };
    const float dt = rbf(expf(bf2f(pdt)));
    float2 C[2], y1[2], z8[2], y128[2];
    float cmax = 0.f;
#pragma unroll
    for (int m = 0; m < 2; m++) {
        const float wr2 = -rbf(expf(__uint_as_float(m ? pla & 0xffff0000u : pla << 16))) * dt * 1.4426950408889634f;
        const float wi = __uint_as_float(m ? pai & 0xffff0000u : pai << 16) * dt;
        C[m] = make_float2(__uint_as_float(m ? pcr & 0xffff0000u : pcr << 16) * dt, -__uint_as_float(m ? pci & 0xffff0000u : pci << 16) * dt);
        cmax = fmaxf(cmax, fmaxf(fabsf(C[m].x), fabsf(C[m].y)));
        y1[m] = cexp_at(wr2, -wi, 1.f); z8[m] = cexp_at(wr2, wi, 8.f); y128[m] = cexp_at(wr2, -wi, 128.f);
    }
    const int ex = min(max((int)(__reduce_max_sync(~0u, __float_as_uint(cmax)) >> 23), 20), 240);
    const float scale = __uint_as_float((uint32_t)(127 + 10 + 127 - ex) << 23), unscale = 2.0f * __uint_as_float((uint32_t)(ex - 10) << 23);
    TSTAMPK(4, 64);
    if (KG_PF >= 2 && tid >= 40 && tid < 72) asm volatile("prefetch.global.L2 [%0];" ::"l"(pfq));
    float k2048 = 0.f;
    float acc[5][4];
#pragma unroll
    for (int j = 0; j < 5; j++)
#pragma unroll
        for (int k = 0; k < 4; k++) acc[j][k] = 0.f;
    uint32_t af[8][4];
    {
        float2 h0[2], h1[2], g0[2], g1[2], g2[2], g2b[2], g3[2], g4[2], y2[2], y4[2];
#pragma unroll
        for (int m = 0; m < 2; m++) {
            h0[m] = make_float2(1.f, 0.f); h1[m] = csqr(csqr(csqr(z8[m])));
            g0[m] = make_float2(C[m].x * scale, C[m].y * scale);
            g1[m] = cmul(g0[m], y128[m]);
            const float2 y256 = csqr(y128[m]), y512 = csqr(y256);
            g2b[m] = g2[m] = cmul(g0[m], y256); g3[m] = cmul(g0[m], y512); g4[m] = cmul(g3[m], y512);
            y2[m] = csqr(y1[m]); y4[m] = csqr(y2[m]);
            const float2 y1024 = csqr(y512);
            k2048 += fmaf(g4[m].x, y1024.x, -g4[m].y * y1024.y);
        }
#pragma unroll
        for (int e = 0; e < 8; e++) {
            sts4(e, 0, packh(h0[0]), packh(h1[0]), packh(h0[1]), packh(h1[1]));
            sts4(e, 4096, packh(g0[0]), packh(g0[1]), packh(g1[0]), packh(g1[1]));
#pragma unroll
            for (int m = 0; m < 2; m++)
                if (e < 7) { h0[m] = e ? cmul(h0[m], z8[m]) : z8[m]; h1[m] = cmul(h1[m], z8[m]); g0[m] = cmul(g0[m], y1[m]); g1[m] = cmul(g1[m], y1[m]); }
            if (e < 5) k2048 += __shfl_xor_sync(~0u, k2048, 1 << e);
        }
        if (KG_PF == 1 && tid >= 40 && tid < 72) asm volatile("prefetch.global.L2 [%0];" ::"l"(pfq));
        __syncwarp();
#pragma unroll
        for (int e = 0; e < 8; e++) {
            uint32_t b[4];
            lds4(e, 0, af[e]); lds4(e, 4096, b);
            sts4(e, 8192, packh(g2[0]), packh(g2[1]), packh((e & 1) ? cmul(g3[0], y4[0]) : g3[0]), packh((e & 1) ? cmul(g3[1], y4[1]) : g3[1]));
            asm volatile("st.shared.v2.u32 [%0], {%1,%2};" ::"r"(stb ^ (e << 3)), "r"(packh(g4[0])), "r"(packh(g4[1])) : "memory");
#pragma unroll
            for (int m = 0; m < 2; m++)
                if (e < 7) {
                    g2[m] = e == 3 ? cmul(g2b[m], y128[m]) : cmul(g2[m], y2[m]);
                    if (e & 1) g3[m] = cmul(g3[m], y128[m]);
                    g4[m] = cmul(g4[m], y128[m]);
                }
            mma_f16(acc[0], af[e][0], af[e][1], af[e][2], af[e][3], b[0], b[1]);
            mma_f16(acc[1], af[e][0], af[e][1], af[e][2], af[e][3], b[2], b[3]);
        }
    }
    TSTAMPK(6, 64);
    const int job = w16 * 128 + blockIdx.x, skb = job / 120, sa = job - 120 * skb;
    __syncwarp();
    if (job < 1200 && elect()) tma_load_3d(tw + 4096, &tmWc, 0, skb * 64, sa, cbar);
#pragma unroll
    for (int sp = 0; sp < 8; sp++) {
        uint32_t c[4], e0, e1;
        lds4(sp, 8192, c);
        asm volatile("ld.shared.v2.u32 {%0,%1}, [%2];" : "=r"(e0), "=r"(e1) : "r"((ldb ^ ((sp & 3) << 3)) + sp * 256) : "memory");
        mma_f16(acc[2], af[sp][0], af[sp][1], af[sp][2], af[sp][3], c[0], c[1]);
        mma_f16(acc[3], af[sp][0], af[sp][1], af[sp][2], af[sp][3], c[2], c[3]);
        mma_f16(acc[4], af[sp][0], af[sp][1], af[sp][2], af[sp][3], e0, e1);
    }
    {
        float* Pp = reinterpret_cast<float*>(tab + warp * 896);
#pragma unroll
        for (int h = 0; h < 2; h++) {
            const int b = g + 8 * h;
            *reinterpret_cast<float2*>(Pp + 8 * b + 2 * t) = make_float2(acc[0][2 * h] * unscale, acc[0][2 * h + 1] * unscale);
            *reinterpret_cast<float2*>(Pp + 128 + 8 * b + 2 * t) = make_float2(acc[1][2 * h] * unscale, acc[1][2 * h + 1] * unscale);
            *reinterpret_cast<float2*>(Pp + 256 + 4 * b + 2 * (t & 1) + 64 * (t >> 1)) = make_float2(acc[2][2 * h] * unscale, acc[2][2 * h + 1] * unscale);
            *reinterpret_cast<float2*>(Pp + 384 + 2 * b + 32 * t) = make_float2(acc[3][2 * h] * unscale, acc[3][2 * h + 1] * unscale);
            Pp[512 + b + 32 * t] = acc[4][2 * h] * unscale;
            Pp[512 + b + 32 * t + 16] = acc[4][2 * h + 1] * unscale;
        }
        if (lane == 0) Pp[640] = k2048 * unscale;
    }
    TSTAMPK(7, 64);
    asm volatile("bar.sync %0, 96;" ::"r"(grp + 1) : "memory");
    TSTAMPK(9, 64);
    const float* Kp = reinterpret_cast<const float*>(tab);
    auto ksum = [&](int i) -> float { return (Kp[i] + Kp[3584 + i]) + Kp[7168 + i]; };
    auto ksum4 = [&](int q) -> float4 {
        const float4 a = reinterpret_cast<const float4*>(Kp)[q], b = reinterpret_cast<const float4*>(Kp)[896 + q], c = reinterpret_cast<const float4*>(Kp)[1792 + q];
        return make_float4((a.x + b.x) + c.x, (a.y + b.y) + c.y, (a.z + b.z) + c.z, (a.w + b.w) + c.w);
    };
    {
        uint2* E4 = reinterpret_cast<uint2*>(in.tap + d * 128);
        float4 v = ksum4(tid), u = ksum4(96 + min(tid, 64));
        const float cor = rbf(ksum(tid == 95 ? 384 : 512));
        if (tid == 95) v.w -= cor;
        if (tid == 31) u.w -= cor;
        const uint32_t lo = pack2(v.x, v.y), hi = pack2(v.z, v.w);
        if (tid < 64) {
            E4[6 + tid] = make_uint2(lo, hi);
            E4[(tid < 32 ? 159 : 209 - 32) + tid] = make_uint2(pack2(u.x, u.y), pack2(u.z, u.w));
        } else {
            const uint32_t nx = __shfl_down_sync(~0u, lo, 1);
            in.tap[d * 128 + 35 + tid - 64] = make_uint4(__byte_perm(lo, 0, 0x1010), __byte_perm(lo, hi, 0x5432), __byte_perm(hi, 0, 0x1010), __byte_perm(hi, tid == 95 ? 0u : nx, 0x5432));
            if (tid == 64) E4[241] = make_uint2(pack2(u.x, 0.f), 0u);
        }
    }
    TSTAMPK(10, 64);
    if (job < 1200) {
        mbar_wait(cbar, 0);
        uint32_t w[4][4];
        float cs[4] = {0.f, 0.f, 0.f, 0.f};
#pragma unroll
        for (int a = 0; a < 4; a++) ldsm_x4_t(w[a], tw + 4096 + ((lane >> 4) * 8 + (lane & 7)) * 32 + ((((lane >> 3) ^ (lane >> 2)) & 1) << 4) + a * 512);
#pragma unroll
        for (int a = 0; a < 4; a++) mma_bf16(cs, w[a][0], w[a][1], w[a][2], w[a][3], 0x3f803f80u, 0x3f803f80u);
        if (t < 2) in.csp[skb * 1920 + sa * 16 + g + 8 * t] = t ? cs[2] : cs[0];
    }
    SPAN(0, 3);
}

#define CV_MODE 0
#define CV_LD __ldcg
#define CV_LDX __ldcg
#define CV_SLEEP 100
constexpr int CV_CPB = 5;
constexpr int CV_THREADS = 512;
constexpr int UPADF = 128;
constexpr int ULEN = UPADF + SEQ + 80;
constexpr int XLEN = SEQ + 16;
constexpr int BX_5 = 0, BX_3 = 3264, BX_9 = 6528, BX_7 = 8960, BX_LEN = 11392;
constexpr int CV_SM_T = 0;
constexpr int CV_SM_B = CV_CPB * TAPB;
constexpr int CV_SM_U = CV_SM_B + CV_CPB * BX_LEN;
constexpr int CV_SM_X = CV_SM_U + CV_CPB * ULEN * 2;
constexpr int CV_SM_Y = CV_SM_X + CV_CPB * XLEN * 2;
constexpr int CV_SM_P = CV_SM_Y + CV_CPB * XLEN * 2;
constexpr int CV_SM_CNT = CV_SM_P + 6 * 4096;
constexpr int CV_SM_O = (CV_SM_CNT + 128 + 127) & ~127;
constexpr int CV_SMEM = CV_SM_O + 20480;
static_assert(CV_SM_B % 128 == 0 && CV_SM_CNT % 16 == 0, "layout");

__device__ __forceinline__ uint32_t sub2(uint32_t x, uint32_t m) {
    const __nv_bfloat162 d = __hsub2(*reinterpret_cast<const __nv_bfloat162*>(&x), *reinterpret_cast<const __nv_bfloat162*>(&m));
    return *reinterpret_cast<const uint32_t*>(&d);
}
__device__ __forceinline__ uint32_t add2(uint32_t x, uint32_t y) {
    const __nv_bfloat162 d = __hadd2_rn(*reinterpret_cast<const __nv_bfloat162*>(&x), *reinterpret_cast<const __nv_bfloat162*>(&y));
    return *reinterpret_cast<const uint32_t*>(&d);
}
__device__ __forceinline__ void cp_async16(uint32_t dst, const void* src) {
    asm volatile("cp.async.cg.shared.global [%0], [%1], 16;" ::"r"(dst), "l"(src));
}
__device__ __forceinline__ void cp_async_wait_all() { asm volatile("cp.async.wait_all;" ::: "memory"); }

template <bool FULL>
__device__ __forceinline__ void direct_pass(float (&acc)[8][4], uint32_t ub, uint32_t o0, uint32_t o1, const uint2* __restrict__ Tp, bool first_half) {
    uint32_t sw[8][8];
#pragma unroll
    for (int j = 0; j < 8; j++) { ldsm_x4(&sw[j][0], ub + o0 + j * 256); ldsm_x4(&sw[j][4], ub + o1 + j * 256); }
#pragma unroll
    for (int M = 0; M < 4; M++) {
#pragma unroll
        for (int i = 0; i < 4; i++) {
            const uint2 hi = Tp[128 * M + 16 * i], lo = Tp[128 * M + 16 * i - 8];
#pragma unroll
            for (int j = FULL ? 0 : M; j < 8; j++) mma_bf16(acc[j], hi.x, hi.y, lo.x, lo.y, sw[(j - M) & 7][2 * i], sw[(j - M) & 7][2 * i + 1]);
        }
        if (FULL) {
            ldsm_x4(&sw[7 - M][0], ub + o0 - (M + 1) * 256);
            if (M < 3) ldsm_x4(&sw[7 - M][4], ub + o1 - (M + 1) * 256);
        }
    }
    if (first_half) {
        const uint2 hi = Tp[512], lo = Tp[504];
#pragma unroll
        for (int j = FULL ? 0 : 4; j < 8; j++) mma_bf16(acc[j], hi.x, hi.y, lo.x, lo.y, sw[(j - 4) & 7][0], sw[(j - 4) & 7][1]);
    }
}
__device__ __forceinline__ uint32_t fin2(uint32_t y, uint32_t u, uint32_t dk) {
    typedef __nv_bfloat162 b2;
    const b2 r = __hadd2_rn(*reinterpret_cast<const b2*>(&y), __hmul2_rn(*reinterpret_cast<const b2*>(&u), *reinterpret_cast<const b2*>(&dk)));
    return *reinterpret_cast<const uint32_t*>(&r);
}
__global__ void __launch_bounds__(CV_THREADS, 1) conv_kernel(const bf16* __restrict__ Dskip, int layer, const uint4* __restrict__ piv, const float4* __restrict__ sum, const bf16* __restrict__ x1T,
                                                             bf16* __restrict__ dst, const uint4* __restrict__ tap, bf16* __restrict__ yT, const __grid_constant__ CUtensorMap tmOut) {
    extern __shared__ __align__(128) unsigned char sm[];
    SPAN(3 + 4 * layer, 0);
    bf16* Us = reinterpret_cast<bf16*>(sm + CV_SM_U);
    bf16* Xs = reinterpret_cast<bf16*>(sm + CV_SM_X);
    bf16* Ys = reinterpret_cast<bf16*>(sm + CV_SM_Y);
    const int tid = threadIdx.x, lane = tid & 31, warp = __shfl_sync(~0u, tid >> 5, 0);
    const int d0 = blockIdx.x * CV_CPB, tile = blockIdx.x; (void)tile;
    const int g = lane >> 2, ti = lane & 3;
    const int e = g - 2 * ti;
    uint32_t lds_off[4];
    uint32_t off2, off3, offc;
    {
        const int mat = lane >> 3, r = lane & 7;
#pragma unroll
        for (int pr = 0; pr < 4; pr++) {
            const int iw = 2 * pr + (mat >> 1), half = mat & 1;
            const int chunk = (UPADF - 16 * iw + 16 * r + 8 * half) >> 3;
            lds_off[pr] = (uint32_t)((chunk ^ ((chunk >> 3) & 1)) * 16);
        }
        const int j2 = 13 + r + 8 * (mat >> 1), j3 = j2 + 2, i0 = 8 * (mat & 1);
        off2 = (j2 & 1) ? BX_3 + (4 * j2 + i0 + 84) * 2 : BX_5 + (4 * j2 + i0 + 80) * 2;
        off3 = ((j3 & 1) ? BX_7 : BX_9) + (8 * j3 + i0 + 136) * 2;
        const int cc = (UPADF + 16 * (r + (mat >> 1)) + i0) >> 3;
        offc = (uint32_t)((cc ^ ((cc >> 3) & 1)) * 16);
    }
#define CV_WX 0
    const int wv = warp ^ CV_WX;
    const uint32_t rtab = wv < 8 ? (wv < 4 ? 0x0B090200u : 0x0C0A0301u) : (wv < 12 ? 0x13111008u : 0x1412241Cu);
    const int rl = (rtab >> (8 * (warp & 3))) & 0xff, type = rl >> 3, c = rl & 7;
    const int H = (type == 1 || type == 2) ? 1 : 0, T0 = 8 * H;
    uint32_t toff = CV_SM_T + c * TAPB + (TPAD + e) * 8;
    uint32_t ubase = smem_u32(Us + c * ULEN);
    const uint32_t bbase = smem_u32(sm + CV_SM_B + c * BX_LEN);
    uint32_t rd0, rd1;
    {
        const uint32_t rstart = wv < 8 ? (wv < 4 ? 0x02000000u : 0x06040000u) : (wv < 12 ? 0x0C0B0A08u : 0x1E1D150Fu);
        const uint32_t rcount = wv < 8 ? 0x02020000u : (wv < 12 ? 0x03010102u : 0x01010806u);
        rd0 = (rstart >> (8 * (warp & 3))) & 0xff; rd1 = rd0 + ((rcount >> (8 * (warp & 3))) & 0xff);
    }
    asm volatile("" : "+r"(lds_off[0]), "+r"(lds_off[1]), "+r"(lds_off[2]), "+r"(lds_off[3]), "+r"(ubase), "+r"(toff), "+r"(rd0), "+r"(rd1));
    const uint2* Tc = reinterpret_cast<const uint2*>(sm + toff);
    TSTAMP1X(9, 256);
    unsigned short dskr;
    asm volatile("ld.global.nc.u16 %0, [%1];" : "=h"(dskr) : "l"(Dskip + d0 + min(lane, CV_CPB - 1)));
    if (tid >= 256) {
        const int t2 = tid - 256;
        if (t2 == 0) {
            mbar_init(smem_u32(sm + CV_SM_CNT) + 104, 1);
            asm volatile("fence.mbarrier_init.release.cluster;" ::: "memory");
            mbar_expect_tx(smem_u32(sm + CV_SM_CNT) + 104, CV_CPB * 2048);
            bulk_load(smem_u32(sm + CV_SM_O), tap + d0 * 128, CV_CPB * 2048, smem_u32(sm + CV_SM_CNT) + 104);
        } else if (lane == 0) {
            mbar_init(smem_u32(sm + CV_SM_CNT) + 16 * (warp - 9), warp == 15 ? 16 : 1);
            if (warp < 15) mbar_init(smem_u32(sm + CV_SM_CNT) + 16 * (warp - 9) + 8, 1);
            else if (layer) prefetch_tmap(&tmOut);
        }
        if (t2 < 149) {
            const int k = t2;
            const int off = k < 18 ? BX_5 + 8 * k : k < 37 ? BX_3 + 8 * (k - 18) : k < 69 ? BX_9 + 8 * (k - 37) : k < 101 ? BX_7 + 8 * (k - 69)
                          : k < 133 ? 8 * (k - 101) : (UPADF + SEQ) * 2 + 8 * (k - 133);
#pragma unroll
            for (int c = 0; c < CV_CPB; c++) *reinterpret_cast<uint2*>(sm + (k < 101 ? CV_SM_B + c * BX_LEN : CV_SM_U + c * ULEN * 2) + off) = make_uint2(0, 0);
        }
        asm volatile("bar.sync 1, 256;" ::: "memory");
        TSTAMP1X(10, 256);
        mbar_wait(smem_u32(sm + CV_SM_CNT) + 104, 0);
        TSTAMP1X(11, 256);
#pragma unroll 1
        for (int r = t2; r < 392; r += 256) {
            const bool dd = r < 272, cc = r >= 368;
            const uint32_t* E2 = reinterpret_cast<const uint32_t*>(sm + CV_SM_O) + (dd ? r + 3 : r < 320 ? 301 + 2 * (r - 272) : cc ? 417 : 401 + 2 * (r - 320));
            const uint32_t* E3 = E2 + (dd ? 4 : cc ? 0 : 1);
            const uint32_t s0 = !cc ? 0x7610u : r == 382 ? 0x1044u : 0x4444u, s1 = !cc ? 0x7610u : r == 378 ? 0x1044u : 0x4444u;
            const uint32_t s2 = !cc ? 0x1032u : r == 381 ? 0x4410u : 0x4444u, s3 = !cc ? 0x1032u : r == 377 ? 0x4410u : 0x4444u;
            uint32_t w[CV_CPB][4];
#pragma unroll
            for (int c = 0; c < CV_CPB; c++) { w[c][0] = E2[512 * c]; w[c][1] = E2[512 * c + 1]; w[c][2] = E3[512 * c]; w[c][3] = E3[512 * c + 1]; }
#pragma unroll
            for (int c = 0; c < CV_CPB; c++) {
                const uint32_t a = __byte_perm(w[c][3], w[c][2], s1), b = __byte_perm(w[c][1], w[c][0], s2);
                *reinterpret_cast<uint4*>(sm + CV_SM_T + c * TAPB + r * 16) =
                    make_uint4(__byte_perm(w[c][1], w[c][0], s0), dd || cc ? a : b, dd || cc ? b : a, __byte_perm(w[c][3], w[c][2], s3));
            }
        }
        TSTAMP1X(12, 256);
        if (layer == 0) {
#pragma unroll
            for (int c = 0; c < CV_CPB; c++) reinterpret_cast<uint4*>(yT + (size_t)(d0 + c) * XCP)[t2] = make_uint4(~0u, ~0u, ~0u, ~0u);
        }
        pdl_sync();
        if (layer && blockIdx.x == 0 && t2 == 0) g_epoch = ld_epoch();
    } else {
        const uint4* ppv = piv + tid;
        const float4* psv = sum + tid;
        const uint2* pxv = reinterpret_cast<const uint2*>(x1T + (size_t)d0 * XCP) + (tid >> 4) * 32 + (tid & 15);
        asm volatile("st.shared.u64 [%0], %1;" ::"r"(smem_u32(Ys) + tid * 8), "l"((uint64_t)ppv ^ (uint64_t)psv ^ (uint64_t)pxv) : "memory");
        pdl_sync();
        SPAN(3 + 4 * layer, 1);
        TSTAMP(0);
        if (threadIdx.x == 0) { GSTAMP(g_tim, 15); }
        float4 sv[4];
#pragma unroll
        for (int k = 0; k < 4; k++) sv[k] = CV_LD(psv + 256 * k);
        const uint4 pv = CV_LD(ppv);
        uint2 xe[CV_CPB], xo[CV_CPB];
#pragma unroll
        for (int c = 0; c < CV_CPB; c++) { xe[c] = CV_LDX(pxv + c * (XCP / 4)); xo[c] = CV_LDX(pxv + c * (XCP / 4) + 16); }
        uint32_t mw[4];
        float rs[8];
#pragma unroll
        for (int k = 0; k < 4; k++) {
            const uint32_t pw = k == 0 ? pv.x : k == 1 ? pv.y : k == 2 ? pv.z : pv.w;
            const float d0_ = sv[k].x * (1.0f / DM), d1_ = sv[k].z * (1.0f / DM);
            mw[k] = pack2(__uint_as_float(pw << 16) + d0_, __uint_as_float(pw & 0xffff0000u) + d1_);
            const uint32_t vr = pack2(fmaxf(fmaf(-d0_, d0_, sv[k].y * (1.0f / DM)), 0.f), fmaxf(fmaf(-d1_, d1_, sv[k].w * (1.0f / DM)), 0.f));
            const uint32_t ve = pack2(__uint_as_float(vr << 16) + 1e-5f, __uint_as_float(vr & 0xffff0000u) + 1e-5f);
            const uint32_t sd = pack2(sqrt_apx(__uint_as_float(ve << 16)), sqrt_apx(__uint_as_float(ve & 0xffff0000u)));
            rs[2 * k] = rcp_apx(__uint_as_float(sd << 16)); rs[2 * k + 1] = rcp_apx(__uint_as_float(sd & 0xffff0000u));
        }
        if (rs[0] != 123.f) TSTAMP(13);
        const int ch = tid + UPADF / 8, pch = ch ^ ((ch >> 3) & 1);
#pragma unroll
        for (int c = 0; c < CV_CPB; c++) {
            *reinterpret_cast<uint4*>(Xs + c * XLEN + tid * 8) = make_uint4(xe[c].x, xe[c].y, xo[c].x, xo[c].y);
            const uint32_t e0 = sub2(xe[c].x, mw[0]), e1 = sub2(xe[c].y, mw[1]), o0 = sub2(xo[c].x, mw[2]), o1 = sub2(xo[c].y, mw[3]);
            *reinterpret_cast<uint4*>(Us + c * ULEN + pch * 8) =
                make_uint4(pack2(__uint_as_float(e0 << 16) * rs[0], __uint_as_float(o0 << 16) * rs[4]), pack2(__uint_as_float(e0 & 0xffff0000u) * rs[1], __uint_as_float(o0 & 0xffff0000u) * rs[5]),
                           pack2(__uint_as_float(e1 << 16) * rs[2], __uint_as_float(o1 << 16) * rs[6]), pack2(__uint_as_float(e1 & 0xffff0000u) * rs[3], __uint_as_float(o1 & 0xffff0000u) * rs[7]));
        }
    }
    __syncthreads();
    TSTAMP(1);
#pragma unroll 1
    for (int rd = rd0; rd < (int)rd1; rd++) {
        const int i = 32 * rd + lane;
        if (i < CV_CPB * 193) {
            const int c = i / 193, chunk = i - c * 193 - 1, ch = chunk + UPADF / 8;
            const bf16* uc = Us + c * ULEN;
            const uint4 o = *reinterpret_cast<const uint4*>(uc + (ch ^ ((ch >> 3) & 1)) * 8);
            const uint2 lo = *reinterpret_cast<const uint2*>(uc + ((ch - 1) ^ (((ch - 1) >> 3) & 1)) * 8 + 4);
            const uint2 hi = *reinterpret_cast<const uint2*>(uc + ((ch + 1) ^ (((ch + 1) >> 3) & 1)) * 8);
            const uint32_t w[8] = {lo.x, lo.y, o.x, o.y, o.z, o.w, hi.x, hi.y};
            float v[16], b[8];
#pragma unroll
            for (int k = 0; k < 8; k++) { v[2 * k] = __uint_as_float(w[k] << 16); v[2 * k + 1] = __uint_as_float(w[k] & 0xffff0000u); }
            unsigned char* bx = sm + CV_SM_B + c * BX_LEN + chunk * 16;
#pragma unroll
            for (int k = 0; k < 8; k++) b[k] = v[k + 4] + (v[k + 3] + v[k + 5]);
            *reinterpret_cast<uint2*>(bx + BX_3 + 168) = make_uint2(pack2(b[0], b[1]), pack2(b[2], b[3]));
            *reinterpret_cast<uint2*>(bx + BX_3 + 176) = make_uint2(pack2(b[4], b[5]), pack2(b[6], b[7]));
#pragma unroll
            for (int k = 0; k < 8; k++) b[k] += v[k + 2] + v[k + 6];
            *reinterpret_cast<uint4*>(bx + BX_5 + 160) = make_uint4(pack2(b[0], b[1]), pack2(b[2], b[3]), pack2(b[4], b[5]), pack2(b[6], b[7]));
            if (chunk < 128) {
#pragma unroll
                for (int k = 0; k < 8; k++) b[k] += v[k + 1] + v[k + 7];
                *reinterpret_cast<uint4*>(bx + BX_7 + 272) = make_uint4(pack2(b[0], b[1]), pack2(b[2], b[3]), pack2(b[4], b[5]), pack2(b[6], b[7]));
#pragma unroll
                for (int k = 0; k < 8; k++) b[k] += v[k] + v[k + 8];
                *reinterpret_cast<uint4*>(bx + BX_9 + 272) = make_uint4(pack2(b[0], b[1]), pack2(b[2], b[3]), pack2(b[4], b[5]), pack2(b[6], b[7]));
            }
        }
    }
    __syncwarp();
    if (lane == 0) mbar_arrive(smem_u32(sm + CV_SM_CNT) + 96);
    TSTAMP(2);
    {
        float acc[8][4];
#pragma unroll
        for (int j = 0; j < 8; j++)
#pragma unroll
            for (int k = 0; k < 4; k++) acc[j][k] = 0.f;
#pragma unroll 1
        for (int pass = (type == 2 || type == 4) ? 1 : 0; pass < ((type == 1 || type == 3) ? 1 : 2); pass++) {
            const uint32_t o0 = pass ? lds_off[2] : lds_off[0], o1 = pass ? lds_off[3] : lds_off[1];
            if (H) direct_pass<true>(acc, ubase + T0 * 256, o0, o1, Tc + 64 * pass, pass == 0);
            else direct_pass<false>(acc, ubase, o0, o1, Tc + 64 * pass, pass == 0);
        }
        TSTAMP(6);
        mbar_wait(smem_u32(sm + CV_SM_CNT) + 96, 0);
        if (type != 1 && type != 4) {
            const uint32_t* w2 = reinterpret_cast<const uint32_t*>(sm + CV_SM_T + c * TAPB + TAP_W2) + (115 - 96) + 4 * g - 2 * ti;
            uint32_t f[10][2];
#pragma unroll
            for (int k = 0; k < 10; k++) { f[k][0] = w2[16 * k]; f[k][1] = w2[16 * k - 8]; }
            const uint32_t ab = bbase + off2 + (2 * T0 + 6) * 128;
            const int kmax = H ? 23 : 8;
            uint32_t a[3][4];
            ldsm_x4_t(a[0], ab);
            ldsm_x4_t(a[1], ab - 128);
#pragma unroll
            for (int kp = 0; kp < 24; kp++) {
                if (kp > kmax) break;
                if (kp < 22) ldsm_x4_t(a[(kp + 2) % 3], ab - min(kp + 2, kmax) * 128);
#pragma unroll
                for (int j = 0; j < 8; j++) {
                    const int ee = 2 * j - 14 + kp;
                    if (ee >= 0 && ee <= 9) mma_bf16(acc[j], a[kp % 3][0], a[kp % 3][1], a[kp % 3][2], a[kp % 3][3], f[ee][0], f[ee][1]);
                }
            }
        }
        TSTAMP(7);
        if (type != 2 && type != 4) {
            const uint32_t* w3 = reinterpret_cast<const uint32_t*>(sm + CV_SM_T + c * TAPB + TAP_W3) + (129 - 96) + 2 * (g - ti);
            uint32_t f[9][2];
#pragma unroll
            for (int k = 0; k < 9; k++) { f[k][0] = w3[16 * k]; f[k][1] = w3[16 * k - 8]; }
            const uint32_t ab = bbase + off3 + (T0 - 2) * 256;
            uint32_t a[3][4];
            ldsm_x4_t(a[0], ab);
            ldsm_x4_t(a[1], ab - H * 256);
#pragma unroll
            for (int kp = 0; kp < 9; kp++) {
                if (kp > T0) break;
                if (kp < 7) ldsm_x4_t(a[(kp + 2) % 3], ab - min(kp + 2, T0) * 256);
#pragma unroll
                for (int j = 0; j < 8; j++) {
                    const int dl = j - 7 + kp;
                    if (dl >= 0 && dl <= 8) mma_bf16(acc[j], a[kp % 3][0], a[kp % 3][1], a[kp % 3][2], a[kp % 3][3], f[dl][0], f[dl][1]);
                }
            }
            const uint2* Dc = reinterpret_cast<const uint2*>(sm + CV_SM_T + c * TAPB + TAP_C) + e;
            const uint2 h63 = Dc[16], h64 = Dc[32], l63 = Dc[8], l64 = Dc[24];
#pragma unroll
            for (int j = 0; j < 8; j++)
                if (j == 7 || H) {
                    uint32_t bq[4];
                    ldsm_x4(bq, ubase + offc + (T0 + j - 8) * 256);
                    mma_bf16(acc[j], h64.x, h64.y, l64.x, l64.y, bq[0], bq[1]);
                    mma_bf16(acc[j], h63.x, h63.y, l63.x, l63.y, bq[2], bq[3]);
                }
        }
        TSTAMP(8);
        int hh = (0x14 >> type) & 1;
        asm volatile("" : "+r"(hh));
        const bool hi_half = hh;
        if (type != 0) {
            const int pair = H ? c : 5;
            float4* give = reinterpret_cast<float4*>(sm + CV_SM_P + pair * 4096 + (hi_half ? 2048 : 0)) + lane;
            const float4* take = reinterpret_cast<const float4*>(sm + CV_SM_P + pair * 4096 + (hi_half ? 0 : 2048)) + lane;
            const uint32_t pb = smem_u32(sm + CV_SM_CNT) + pair * 16;
#pragma unroll
            for (int j = 0; j < 8; j++)
                asm volatile("{\n.reg .pred p;\nsetp.eq.s32 p, %5, %6;\n@p st.shared.v4.f32 [%0], {%1,%2,%3,%4};\n}"
                             ::"r"(smem_u32(give + 32 * (j & 3))), "f"(acc[j][0]), "f"(acc[j][1]), "f"(acc[j][2]), "f"(acc[j][3]), "r"(hh), "r"(j < 4 ? 1 : 0) : "memory");
            __syncwarp();
            if (lane == 0) mbar_arrive(pb + (hi_half ? 8 : 0));
            mbar_wait(pb + (hi_half ? 0 : 8), 0);
#pragma unroll
            for (int j = 0; j < 4; j++) {
                const float4 v = take[32 * j];
                acc[j][0] = (hi_half ? acc[j + 4][0] : acc[j][0]) + v.x; acc[j][1] = (hi_half ? acc[j + 4][1] : acc[j][1]) + v.y;
                acc[j][2] = (hi_half ? acc[j + 4][2] : acc[j][2]) + v.z; acc[j][3] = (hi_half ? acc[j + 4][3] : acc[j][3]) + v.w;
            }
        }
        const uint32_t dk = __shfl_sync(~0u, (uint32_t)dskr, c) * 0x10001u;
#pragma unroll 1
        for (int rnd = 0; rnd < (type == 0 ? 2 : 1); rnd++) {
            const int Q = 2 * H + (hi_half ? 1 : rnd);
            if (rnd) {
#pragma unroll
                for (int j = 0; j < 4; j++)
#pragma unroll
                    for (int k = 0; k < 4; k++) acc[j][k] = acc[j + 4][k];
            }
            const uint32_t ya = smem_u32(Ys + c * XLEN) + (128 * (4 * Q + (lane >> 4)) + 16 * (lane & 7) + 8 * ((lane >> 3) & 1)) * 2;
#pragma unroll
            for (int j = 0; j < 4; j += 2)
                asm volatile("stmatrix.sync.aligned.m8n8.x4.trans.shared.b16 [%0], {%1,%2,%3,%4};" ::"r"(ya + j * 256),
                             "r"(pack2(acc[j][0], acc[j][1])), "r"(pack2(acc[j][2], acc[j][3])),
                             "r"(pack2(acc[j + 1][0], acc[j + 1][1])), "r"(pack2(acc[j + 1][2], acc[j + 1][3])) : "memory");
            __syncwarp();
            uint4 yv[2], xv[2], uv[2];
#pragma unroll
            for (int k = 0; k < 2; k++) {
                const int t = 512 * Q + 256 * k + 8 * lane, cu = (t + UPADF) >> 3;
                yv[k] = *reinterpret_cast<const uint4*>(Ys + c * XLEN + t);
                xv[k] = *reinterpret_cast<const uint4*>(Xs + c * XLEN + t);
                uv[k] = *reinterpret_cast<const uint4*>(Us + c * ULEN + (cu ^ ((cu >> 3) & 1)) * 8);
            }
#pragma unroll
            for (int k = 0; k < 2; k++) {
                const uint32_t z0 = fin2(yv[k].x, uv[k].x, dk), z1 = fin2(yv[k].y, uv[k].y, dk), z2 = fin2(yv[k].z, uv[k].z, dk), z3 = fin2(yv[k].w, uv[k].w, dk);
                if (layer)
                    asm volatile("st.relaxed.gpu.global.v4.u32 [%0], {%1,%2,%3,%4};" ::"l"(dst + (size_t)(d0 + c) * XCP + 512 * Q + 256 * k + 8 * lane),
                                 "r"(add2(__byte_perm(xv[k].x, xv[k].z, 0x5410), z0)), "r"(add2(__byte_perm(xv[k].x, xv[k].z, 0x7632), z1)),
                                 "r"(add2(__byte_perm(xv[k].y, xv[k].w, 0x5410), z2)), "r"(add2(__byte_perm(xv[k].y, xv[k].w, 0x7632), z3)) : "memory");
                else {
                    uint2* dp = reinterpret_cast<uint2*>(dst + (size_t)(d0 + c) * XCP + 512 * Q + 256 * k) + (lane >> 4) * 32 + (lane & 15);
                    dp[0] = make_uint2(add2(xv[k].x, __byte_perm(z0, z1, 0x5410)), add2(xv[k].y, __byte_perm(z2, z3, 0x5410)));
                    dp[16] = make_uint2(add2(xv[k].z, __byte_perm(z0, z1, 0x7632)), add2(xv[k].w, __byte_perm(z2, z3, 0x7632)));
                }
            }
        }
        TSTAMP(4);
        if (layer == 1) {
            const int mb = blockIdx.x >> 3, cg = blockIdx.x & 7;
            const bf16* src = dst + (size_t)(cg * 80 + (tid >> 4)) * XCP + mb * 128 + (tid & 15) * 8;
            uint32_t v[3][4];
            __syncthreads();
            TSTAMP(5);
            uint32_t todo = warp < 8 ? 7 : 3;
#pragma unroll 1
            for (int it = 0; it < SPIN_MAX; it++) {
#pragma unroll
                for (int k = 0; k < 3; k++)
                    if (todo >> k & 1)
                        asm volatile("ld.relaxed.gpu.global.v4.u32 {%0,%1,%2,%3}, [%4];" : "=r"(v[k][0]), "=r"(v[k][1]), "=r"(v[k][2]), "=r"(v[k][3]) : "l"(src + k * (32 * XCP)) : "memory");
#pragma unroll
                for (int k = 0; k < 3; k++)
                    if ((todo >> k & 1) && v[k][0] != ~0u && v[k][1] != ~0u && v[k][2] != ~0u && v[k][3] != ~0u) {
                        *reinterpret_cast<uint4*>(sm + (32 * k + (tid >> 4)) * 272 + (tid & 15) * 16) = make_uint4(v[k][0], v[k][1], v[k][2], v[k][3]);
                        todo ^= 1u << k;
                    }
                if (!todo) break;
                __nanosleep(CV_SLEEP);
            }
            __syncthreads();
            uint32_t w[12];
#pragma unroll
            for (int k = 0; k < 3; k++) ldsm_x4(&w[4 * k], smem_u32(sm) + min(32 * k + lane, 79) * 272 + warp * 16);
            const uint32_t ot = smem_u32(sm + CV_SM_O) + warp * 1280, oa = ot + (lane & 7) * 160 + (lane >> 3) * 16;
            stsm_x4_t(oa, w[0], w[1], w[2], w[3]);
            stsm_x4_t(oa + 64, w[4], w[5], w[6], w[7]);
            asm volatile("stmatrix.sync.aligned.m8n8.x2.trans.shared.b16 [%0], {%1,%2};" ::"r"(oa + 128), "r"(w[8]), "r"(w[9]) : "memory");
            fence_async_smem();
            __syncwarp();
            if (lane == 0) tma_store_2d(&tmOut, cg * 80, mb * 128 + 8 * warp, ot);
        }
    }
    TSTAMP(3);
    GSTAMP(g_tim, 14);
    SPAN(3 + 4 * layer, 3);
}

__device__ __forceinline__ void wgmma_fence() { asm volatile("wgmma.fence.sync.aligned;" ::: "memory"); }
__device__ __forceinline__ void wgmma_commit() { asm volatile("wgmma.commit_group.sync.aligned;" ::: "memory"); }
template <int N> __device__ __forceinline__ void wgmma_wait() { asm volatile("wgmma.wait_group.sync.aligned %0;" ::"n"(N) : "memory"); }
__device__ __forceinline__ uint64_t make_desc(uint32_t addr, uint32_t lbo, uint32_t sbo, uint32_t mode) {
    return (uint64_t)((addr & 0x3FFFF) >> 4) | ((uint64_t)(lbo >> 4) << 16) | ((uint64_t)(sbo >> 4) << 32) | ((uint64_t)mode << 62);
}
template <int TA, int TB>
__device__ __forceinline__ void wgmma_n240(float (&d)[120], uint64_t da, uint64_t db, int acc) {
    asm volatile("{\n.reg .pred p;\nsetp.ne.b32 p, %124, 0;\nwgmma.mma_async.sync.aligned.m64n240k16.f32.bf16.bf16 {%0,%1,%2,%3,%4,%5,%6,%7,%8,%9,%10,%11,%12,%13,%14,%15,%16,%17,%18,%19,%20,%21,%22,%23,%24,%25,%26,%27,%28,%29,%30,%31,%32,%33,%34,%35,%36,%37,%38,%39,%40,%41,%42,%43,%44,%45,%46,%47,%48,%49,%50,%51,%52,%53,%54,%55,%56,%57,%58,%59,%60,%61,%62,%63,%64,%65,%66,%67,%68,%69,%70,%71,%72,%73,%74,%75,%76,%77,%78,%79,%80,%81,%82,%83,%84,%85,%86,%87,%88,%89,%90,%91,%92,%93,%94,%95,%96,%97,%98,%99,%100,%101,%102,%103,%104,%105,%106,%107,%108,%109,%110,%111,%112,%113,%114,%115,%116,%117,%118,%119}, %120, %121, p, 1, 1, %122, %123;\n}"
                 : "+f"(d[0]), "+f"(d[1]), "+f"(d[2]), "+f"(d[3]), "+f"(d[4]), "+f"(d[5]), "+f"(d[6]), "+f"(d[7]), "+f"(d[8]), "+f"(d[9]), "+f"(d[10]), "+f"(d[11]), "+f"(d[12]), "+f"(d[13]), "+f"(d[14]), "+f"(d[15]), "+f"(d[16]), "+f"(d[17]), "+f"(d[18]), "+f"(d[19]), "+f"(d[20]), "+f"(d[21]), "+f"(d[22]), "+f"(d[23]), "+f"(d[24]), "+f"(d[25]), "+f"(d[26]), "+f"(d[27]), "+f"(d[28]), "+f"(d[29]), "+f"(d[30]), "+f"(d[31]), "+f"(d[32]), "+f"(d[33]), "+f"(d[34]), "+f"(d[35]), "+f"(d[36]), "+f"(d[37]), "+f"(d[38]), "+f"(d[39]), "+f"(d[40]), "+f"(d[41]), "+f"(d[42]), "+f"(d[43]), "+f"(d[44]), "+f"(d[45]), "+f"(d[46]), "+f"(d[47]), "+f"(d[48]), "+f"(d[49]), "+f"(d[50]), "+f"(d[51]), "+f"(d[52]), "+f"(d[53]), "+f"(d[54]), "+f"(d[55]), "+f"(d[56]), "+f"(d[57]), "+f"(d[58]), "+f"(d[59]), "+f"(d[60]), "+f"(d[61]), "+f"(d[62]), "+f"(d[63]), "+f"(d[64]), "+f"(d[65]), "+f"(d[66]), "+f"(d[67]), "+f"(d[68]), "+f"(d[69]), "+f"(d[70]), "+f"(d[71]), "+f"(d[72]), "+f"(d[73]), "+f"(d[74]), "+f"(d[75]), "+f"(d[76]), "+f"(d[77]), "+f"(d[78]), "+f"(d[79]), "+f"(d[80]), "+f"(d[81]), "+f"(d[82]), "+f"(d[83]), "+f"(d[84]), "+f"(d[85]), "+f"(d[86]), "+f"(d[87]), "+f"(d[88]), "+f"(d[89]), "+f"(d[90]), "+f"(d[91]), "+f"(d[92]), "+f"(d[93]), "+f"(d[94]), "+f"(d[95]), "+f"(d[96]), "+f"(d[97]), "+f"(d[98]), "+f"(d[99]), "+f"(d[100]), "+f"(d[101]), "+f"(d[102]), "+f"(d[103]), "+f"(d[104]), "+f"(d[105]), "+f"(d[106]), "+f"(d[107]), "+f"(d[108]), "+f"(d[109]), "+f"(d[110]), "+f"(d[111]), "+f"(d[112]), "+f"(d[113]), "+f"(d[114]), "+f"(d[115]), "+f"(d[116]), "+f"(d[117]), "+f"(d[118]), "+f"(d[119])
                 : "l"(da), "l"(db), "n"(TA), "n"(TB), "r"(acc));
}

__device__ __forceinline__ void wgmma_n80(float (&d)[40], uint64_t da, uint64_t db, int acc) {
    asm volatile("{\n.reg .pred p;\nsetp.ne.b32 p, %42, 0;\nwgmma.mma_async.sync.aligned.m64n80k16.f32.bf16.bf16 {%0,%1,%2,%3,%4,%5,%6,%7,%8,%9,%10,%11,%12,%13,%14,%15,%16,%17,%18,%19,%20,%21,%22,%23,%24,%25,%26,%27,%28,%29,%30,%31,%32,%33,%34,%35,%36,%37,%38,%39}, %40, %41, p, 1, 1, 0, 1;\n}"
                 : "+f"(d[0]), "+f"(d[1]), "+f"(d[2]), "+f"(d[3]), "+f"(d[4]), "+f"(d[5]), "+f"(d[6]), "+f"(d[7]), "+f"(d[8]), "+f"(d[9]), "+f"(d[10]), "+f"(d[11]), "+f"(d[12]), "+f"(d[13]), "+f"(d[14]), "+f"(d[15]), "+f"(d[16]), "+f"(d[17]), "+f"(d[18]), "+f"(d[19]), "+f"(d[20]), "+f"(d[21]), "+f"(d[22]), "+f"(d[23]), "+f"(d[24]), "+f"(d[25]), "+f"(d[26]), "+f"(d[27]), "+f"(d[28]), "+f"(d[29]), "+f"(d[30]), "+f"(d[31]), "+f"(d[32]), "+f"(d[33]), "+f"(d[34]), "+f"(d[35]), "+f"(d[36]), "+f"(d[37]), "+f"(d[38]), "+f"(d[39])
                 : "l"(da), "l"(db), "r"(acc));
}

constexpr int A1_THREADS = 384;
constexpr int A1_NST = 4;
#define A1_SKEW 8
constexpr int A1_STAGE = 16384 + WQ_STAGE;
constexpr int A1_KVP = 336;
constexpr int A1_SM_KV = 2 * A1_STAGE;
constexpr int A1_SM_BAR = A1_NST * A1_STAGE;
constexpr int A1_SM_RS = A1_SM_BAR + 512;
constexpr int A1_SM_W0 = A1_SM_BAR + 3072, A1_SM_W3 = A1_SM_BAR - 3 * WOB, A1_SM_A1 = 2 * WOB, A1_SM_A0 = A1_SM_A1 + 61440;
constexpr int A1_SM_XA = A1_SM_W0 + 2 * WOB, A1_SM_XB = A1_SM_XA + 2048;
constexpr int A1_SMEM = A1_SM_W0 + 3 * WOB;
static_assert(A1_SM_W3 >= A1_SM_KV + 144 * A1_KVP && A1_SM_W3 % 512 == 0 && A1_SM_A1 % 1024 == 0 && A1_SM_A0 <= A1_SM_KV && A1_SM_A0 + 61440 <= A1_SM_W3 && A1_SMEM <= 232448, "layout");
__device__ __forceinline__ constexpr uint32_t wo_off(int h) { return h * WOB + (h < 3 ? A1_SM_W0 : h < 6 ? A1_SM_W3 - 3 * WOB : -6 * WOB); }
#define A1_FRED "red.relaxed.gpu.global.add.u32"
#define A1_FLD "ld.acquire.gpu.global.u32"
#define ST_SLEEP 20
#define ST_SLEEP0 300
#define WO_LATE bar_done
#define A1_P0 2
#define A1_PW (kb - 2)
#define A1_FSPIN SPIN_MAX
#define A1_FSLEEP 40
#define A1_WOAT 6

template <int L>
__device__ __forceinline__ void a1_mainloop(float (&acc)[120], uint32_t sbase, uint32_t bars, int wg, int tile) {
    constexpr int layer = L; (void)layer;
    const uint64_t da0 = L ? make_desc(sbase + wg * 8192, 8192, 1024, 1) : make_desc(sbase + wg * 8192, 16, 1024, 1), db0 = make_desc(sbase + 16384, 1024, 256, 3);
#pragma unroll 1
    for (int t = 0;; t++) {
        const int st = t % A1_NST;
        mbar_wait(bars + 8 * st, (t / A1_NST) & 1);
        if (t == A1_SKEW && wg == 0) mbar_wait(bars + 160, 0);
        TSTAMP3(1 + t);
        wgmma_fence();
#pragma unroll
        for (int kk = 0; kk < 4; kk++) wgmma_n240<L, 1>(acc, da0 + (uint32_t)(st * (A1_STAGE / 16) + kk * (L ? 128 : 2)), db0 + (uint32_t)(st * (A1_STAGE / 16) + (kk >> 1) * (WQ_STAGE / 32) + (kk & 1) * 32), kk ? 1 : t);
        wgmma_commit();
        if (t == 9) break;
        if (t == A1_SKEW - 1 && wg == 0) wgmma_wait<0>(); else wgmma_wait<1>();
        if (t > 0 && (threadIdx.x & 127) == 0) {
            if (t != A1_SKEW || wg) mbar_arrive(bars + 8 * (A1_NST + (t - 1) % A1_NST));
            if (t == A1_SKEW - 1 && wg == 0) mbar_arrive(bars + 8 * (A1_NST + t % A1_NST));
        }
    }
}

__global__ void __launch_bounds__(A1_THREADS, 1) a1_kernel(const int layer, const bf16* __restrict__ x0, const unsigned char* __restrict__ wq, const unsigned char* __restrict__ wo,
                                                           float2* __restrict__ rsum, uint4* __restrict__ of, const __grid_constant__ CUtensorMap tmX,
                                                           const __grid_constant__ CUtensorMap tmR, const __grid_constant__ CUtensorMap tmX1, const __grid_constant__ TileTab tab) {
    extern __shared__ __align__(1024) unsigned char stg[];
    const uint32_t sbase = smem_u32(stg);
    const uint32_t bars = sbase + A1_SM_BAR;
    const uint32_t bar_stat = bars + 64, bar_kv = bars + 72, bar_rd = bars + 168;
    const uint32_t bar_wo = bars + 208, bar_done = bars + 216, bar_pv = bars + 224, bar_kvf = bars + 232, bar_f2 = bars + 248, bar_e2 = bars + 384, que = bars + 448;
    const int tid = threadIdx.x;
    const int w = __shfl_sync(~0u, tid >> 5, 0), wg = w >> 2;
    uint32_t smid, ns;
    asm volatile("mov.u32 %0, %smid;" : "=r"(smid));
    asm volatile("mov.u32 %0, %nsmid;" : "=r"(ns));
    const auto te = tab.e[ns == tab.ns ? smid : 132 + blockIdx.x];
    const int tile = te.tile, mb = te.mb, hg = te.hg;
    float2* rst = reinterpret_cast<float2*>(stg + A1_SM_RS) + 8;
    auto issue_w = [&](int it) { bulk_load(sbase + (it % A1_NST) * A1_STAGE + 16384, wq + te.woff + it * WQ_STAGE, WQ_STAGE, bars + 8 * (it % A1_NST)); };
    auto issue_x = [&](int it, int kb) {
        asm volatile("cp.async.bulk.tensor.5d.shared::cluster.global.mbarrier::complete_tx::bytes [%0], [%1, {%3, %3, %3, %4, %5}], [%2];"
                     ::"r"(sbase + (it % A1_NST) * A1_STAGE), "l"(&tmX), "r"(bars + 8 * (it % A1_NST)), "r"(0), "r"(mb), "r"(kb) : "memory");
    };
    if (w == 8 && tile < 128) {
        const bool one = elect();
        if (one) {
#pragma unroll
            for (int i = 0; i < A1_NST; i++) mbar_init(bars + 8 * i, 1);
            asm volatile("fence.mbarrier_init.release.cluster;" ::: "memory");
        }
        __syncwarp();
        asm volatile("bar.arrive 0, 384;" ::: "memory");
        if (one) {
#define PW asm volatile("griddepcontrol.wait;" ::: "memory");
            if (layer) { issue_w(0); PW issue_x(0, te.kb0); issue_x(1, te.kb0 + 1); }
            else { issue_x(0, te.kb0); issue_x(1, te.kb0 + 1); PW issue_w(0); }
            issue_w(1);
#pragma unroll
            for (int i = 0; i < A1_NST; i++) mbar_expect_tx(bars + 8 * i, A1_STAGE);
            asm volatile("griddepcontrol.launch_dependents;" ::: "memory");
#pragma unroll
            for (int kb = 2; kb < A1_P0; kb++) { issue_x(kb, te.kb0 + kb); issue_w(kb); }
            DBGC(34); DBGV(33, smid); DBGV(40, t_entry); DBGV(30, t_a); DBGV(31, t_b); DBGV(32, t_c); DBGV(38, t_d); DBGV(39, t_e);
        }
    }
    if (tile >= 128) { sm_idle(layer); return; }
    if (wg == 2) {
        if (w != 8) {
            if (tid == 320) { prefetch_tmap(&tmX); prefetch_tmap(&tmR); prefetch_tmap(&tmX1); }
            asm volatile("bar.sync 0, 384;" ::: "memory");
        }
        if (w == 9) {
            asm volatile("bar.arrive 3, 64;" ::: "memory");
            if (layer == 0) pdl_sync();
            float4 a[2] = {};
#pragma unroll
            for (int k = 0; k < 10; k++)
#pragma unroll
                for (int h = 0; h < 2; h++) {
                    const int c4 = min(tid - 288 + 32 * h, 59);
                    const float4 v = __ldcg(reinterpret_cast<const float4*>(g_csp + k * 1920 + hg * 80) + c4 + (c4 / 20) * 140);
                    a[h].x += v.x; a[h].y += v.y; a[h].z += v.z; a[h].w += v.w;
                }
#pragma unroll
            for (int h = 0; h < 2; h++)
#pragma unroll
                for (int k = 0; k < 4; k++) {
                    const float c = 0.5f * (k == 0 ? a[h].x : k == 1 ? a[h].y : k == 2 ? a[h].z : a[h].w), c1 = c - rbf(c), c2 = c1 - rbf(c1);
                    *reinterpret_cast<uint4*>(stg + A1_SM_XB + (4 * min(tid - 288 + 32 * h, 59) + k) * 16) = make_uint4(pack2(c, c1), pack2(c2, 0.f), 0u, 0u);
                }
            fence_async_smem();
            __syncwarp();
            if (tid == 288) mbar_arrive(bar_stat);
#pragma unroll 4
            for (int k = 0; k < 40; k++) asm volatile("st.global.v4.u32 [%0], {%1,%1,%1,%1};" ::"l"(of + (mb * 8 + hg) * 1280 + 32 * k + (tid - 288)), "r"(~0u) : "memory");
            asm volatile("fence.acq_rel.gpu;" ::: "memory");
            asm volatile("fence.proxy.async.global;" ::: "memory");
            __syncwarp();
            if (tid == 288) mbar_arrive(bar_done);
            TSTAMP1T(9, 288);
        } else if (w == 8) {
            asm volatile("bar.sync 3, 64;" ::: "memory");
            if (elect()) {
#pragma unroll 1
                for (int kb = A1_P0; kb < 10; kb++) {
                    if (kb < A1_NST) mbar_wait(bars + 8 * A1_PW, 0);
                    else {
                        mbar_wait(bars + 8 * (A1_NST + kb % A1_NST), ((kb / A1_NST) - 1) & 1);
                        if (layer && kb < 9) mbar_wait(bar_rd + 8 * (kb - A1_NST), 0);
                        mbar_expect_tx(bars + 8 * (kb % A1_NST), A1_STAGE);
                    }
                    issue_x(kb, kb < 5 ? kb + te.kb0 : kb - te.kb0); issue_w(kb);
                    if (kb == A1_WOAT) {
                        mbar_expect_tx(bar_wo, 8 * WOB);
                        bulk_load(sbase + A1_SM_W0, wo + hg * 8 * WOB, 2 * WOB, bar_wo);
                    }
                }
                TSTAMP1T(6, 256);
                mbar_wait(bars + 8 * (A1_NST + 3), 1);
                bulk_load(sbase + A1_SM_W3, wo + (hg * 8 + 3) * WOB, 3 * WOB, bar_wo);
            }
            __syncwarp();
        } else {
            const int j = tid - 320;
            const uint32_t tag = ld_epoch();
            if (tid == 352) sm_started(layer);
            if (layer == 0) {
                const uint4* src = reinterpret_cast<const uint4*>(x0 + (size_t)(mb * 128 + hg * 16 + (j >> 2)) * DM);
                uint4 v[20];
#pragma unroll
                for (int k = 0; k < 20; k++) v[k] = __ldg(src + (j & 3) + 4 * k);
                const float p0 = __uint_as_float(__shfl_sync(~0u, v[0].x, j & 28) << 16);
                float s[2] = {0.f, 0.f}, q[2] = {0.f, 0.f};
#pragma unroll
                for (int k = 0; k < 20; k++) {
                    const uint32_t w[4] = {v[k].x, v[k].y, v[k].z, v[k].w};
#pragma unroll
                    for (int i = 0; i < 4; i++) {
                        const float a = __uint_as_float(w[i] << 16) - p0, b = __uint_as_float(w[i] & 0xffff0000u) - p0;
                        s[0] += a; s[1] += b; q[0] = fmaf(a, a, q[0]); q[1] = fmaf(b, b, q[1]);
                    }
                }
                float s0 = s[0] + s[1], q0 = q[0] + q[1];
#pragma unroll
                for (int o = 1; o <= 2; o <<= 1) { s0 += __shfl_xor_sync(~0u, s0, o); q0 += __shfl_xor_sync(~0u, q0, o); }
                if ((j & 3) == 0) {
                    const float d = s0 * (1.0f / DM);
                    const uint32_t ms = pack2(p0 + d, sqrt_apx(rbf(rbf(fmaxf(fmaf(-d, d, q0 * (1.0f / DM)), 0.f)) + 1e-5f)));
                    asm volatile("st.global.cg.u64 [%0], %1;" ::"l"(g_rstat + mb * 128 + (j & 4) * 16 + hg * 8 + (j >> 3)), "l"(tagw(ms, tag)) : "memory");
                    g_piv[mb * 128 + hg * 16 + ((j >> 2) & 8) + (j & 4) + ((j >> 3) & 3)] = __ushort_as_bfloat16((unsigned short)ms);
                }
            }
            float o[4];
            int row;
            if (layer == 0) {
                ulonglong2 v;
#pragma unroll 1
                for (int it = 0; it < SPIN_MAX; it++) {
                    v = ld_tag2(reinterpret_cast<const ulonglong2*>(g_rstat + mb * 128) + j);
                    if (tag_ok(v, tag)) break;
                    __nanosleep(100);
                }
                o[0] = __uint_as_float((uint32_t)v.x << 16); o[1] = rcp_apx(__uint_as_float((uint32_t)v.x & 0xffff0000u));
                o[2] = __uint_as_float((uint32_t)v.y << 16); o[3] = rcp_apx(__uint_as_float((uint32_t)v.y & 0xffff0000u));
                row = 2 * j;
            } else {
                const int ch = j & 7, kg = (j >> 3) & 3;
                const unsigned char* src = stg + (j >> 5) * 8192 + (hg & 3) * 2048;
                float s[8], q[8], p0[8];
#pragma unroll
                for (int i = 0; i < 8; i++) { s[i] = 0.f; q[i] = 0.f; }
#pragma unroll 1
                for (int it = 0; it < 5; it++) {
                    uint4 v[4];
                    mbar_wait(bars + 8 * (it % A1_NST), it / A1_NST);
#pragma unroll
                    for (int k = 0; k < 4; k++) v[k] = *reinterpret_cast<const uint4*>(src + (it % A1_NST) * A1_STAGE + (4 * k + kg) * 128 + ((ch ^ ((4 * k + kg) & 7)) << 4));
                    if (it == 0) {
                        const uint4 pv = *reinterpret_cast<const uint4*>(src + (ch << 4));
                        const uint32_t w[4] = {pv.x, pv.y, pv.z, pv.w};
#pragma unroll
                        for (int i = 0; i < 4; i++) { p0[2 * i] = __uint_as_float(w[i] << 16); p0[2 * i + 1] = __uint_as_float(w[i] & 0xffff0000u); }
                    }
                    asm volatile("" :: "r"(v[0].x), "r"(v[1].x), "r"(v[2].x), "r"(v[3].x), "f"(p0[0]) : "memory");
                    __syncwarp();
                    if ((tid & 31) == 0) mbar_arrive(bar_rd + 8 * it);
#pragma unroll
                    for (int k = 0; k < 4; k++) {
                        const uint32_t w[4] = {v[k].x, v[k].y, v[k].z, v[k].w};
#pragma unroll
                        for (int i = 0; i < 4; i++) {
                            const float a = __uint_as_float(w[i] << 16) - p0[2 * i], b = __uint_as_float(w[i] & 0xffff0000u) - p0[2 * i + 1];
                            s[2 * i] += a; s[2 * i + 1] += b; q[2 * i] = fmaf(a, a, q[2 * i]); q[2 * i + 1] = fmaf(b, b, q[2 * i + 1]);
                        }
                    }
                }
#pragma unroll
                for (int i = 0; i < 4; i++) {
                    const bool up = kg & 2;
                    const float ss = __shfl_xor_sync(~0u, up ? s[i] : s[i + 4], 16), qq = __shfl_xor_sync(~0u, up ? q[i] : q[i + 4], 16);
                    s[i] = (up ? s[i + 4] : s[i]) + ss; q[i] = (up ? q[i + 4] : q[i]) + qq; p0[i] = up ? p0[i + 4] : p0[i];
                }
#pragma unroll
                for (int i = 0; i < 2; i++) {
                    const bool up = kg & 1;
                    const float ss = __shfl_xor_sync(~0u, up ? s[i] : s[i + 2], 8), qq = __shfl_xor_sync(~0u, up ? q[i] : q[i + 2], 8);
                    s[i] = (up ? s[i + 2] : s[i]) + ss; q[i] = (up ? q[i + 2] : q[i]) + qq; p0[i] = up ? p0[i + 2] : p0[i];
                }
                uint4* gp = g_halo + 86016 + mb * 512 + j;
                const float d0 = s[0] * (1.0f / 80.0f), d1 = s[1] * (1.0f / 80.0f);
                asm volatile("st.relaxed.gpu.global.v4.f32 [%0], {%1,%2,%3,%4};" ::"l"(gp + hg * 64), "f"(p0[0] + d0), "f"(fmaxf(fmaf(-d0, s[0], q[0]), 0.f)), "f"(p0[1] + d1), "f"(fmaxf(fmaf(-d1, s[1], q[1]), 0.f)) : "memory");
                __nanosleep(ST_SLEEP0);
                uint32_t pw[8][4], todo = 0xff;
#pragma unroll 1
                for (int it = 0; it < SPIN_MAX; it++) {
#pragma unroll
                    for (int k = 0; k < 8; k++)
                        if (todo >> k & 1) asm volatile("ld.relaxed.gpu.global.v4.u32 {%0,%1,%2,%3}, [%4];" : "=r"(pw[k][0]), "=r"(pw[k][1]), "=r"(pw[k][2]), "=r"(pw[k][3]) : "l"(gp + k * 64) : "memory");
#pragma unroll
                    for (int k = 0; k < 8; k++)
                        if (__all_sync(~0u, pw[k][0] != ~0u && pw[k][1] != ~0u && pw[k][2] != ~0u && pw[k][3] != ~0u)) todo &= ~(1u << k);
                    if (!todo) break;
                    __nanosleep(ST_SLEEP);
                }
#pragma unroll
                for (int r = 0; r < 2; r++) {
                    float mean = 0.f, m2 = 0.f;
#pragma unroll
                    for (int k = 0; k < 8; k++) mean += __uint_as_float(pw[k][2 * r]);
                    mean *= 0.125f;
#pragma unroll
                    for (int k = 0; k < 8; k++) {
                        const float dm = __uint_as_float(pw[k][2 * r]) - mean;
                        m2 += fmaf(80.0f * dm, dm, __uint_as_float(pw[k][2 * r + 1]));
                    }
                    o[2 * r] = rbf(mean);
                    o[2 * r + 1] = rcp_apx(rbf(sqrt_apx(rbf(rbf(m2 * (1.0f / DM)) + 1e-5f))));
                }
                row = (j >> 5) * 64 + (j & 7) * 8 + ((j >> 3) & 3) * 2;
                if (hg == 0) *reinterpret_cast<uint32_t*>(g_piv + SEQ + mb * 128 + 2 * (row & 60) + 4 * (row >> 6) + (row & 3)) = __byte_perm(__float_as_uint(o[0]), __float_as_uint(o[2]), 0x7632);
            }
#pragma unroll
            for (int r = 0; r < 2; r++)
                *reinterpret_cast<uint4*>(stg + A1_SM_XA + (row + r) * 16) = make_uint4(__byte_perm(__float_as_uint(-o[2 * r]), 0, 0x3232), __float_as_uint(-o[2 * r]) >> 16, 0u, 0u);
            *reinterpret_cast<float4*>(rst + row + (row >> 6) * 8) = make_float4(o[0], o[1], o[2], o[3]);
            fence_async_smem();
            TSTAMP1T(7, 320);
            if (tid == 320) DBGC(44);
            __syncwarp();
            if ((tid & 31) == 0) mbar_arrive(bar_stat);
        }
        if (tid == 320) DBGCAL(0);
        if (tid == 352) {
            mbar_wait(WO_LATE, 0);
            mbar_wait(bar_done, 0);
            bulk_load(sbase, wo + (hg * 8 + 6) * WOB, 2 * WOB, bar_wo);
            bulk_load(sbase + A1_SM_W0 + 2 * WOB, wo + (hg * 8 + 2) * WOB, WOB, bar_wo);
        }
        if (w < 10) {
            const int cw = w - 8;
            const uint32_t* fl = reinterpret_cast<const uint32_t*>(rsum + 2 * SEQ) + (((layer * 16 + mb) * 2 + cw) * 8 + (tid & 7)) * FSTR;
            const unsigned char* src = reinterpret_cast<const unsigned char*>(of) + mb * 163840 + cw * 10240 + (tid & 7) * 20480;
            const uint32_t sl = sbase + (cw ? A1_SM_A1 : A1_SM_A0);
            mbar_wait(cw ? bar_done : bar_kvf, 0);
            if ((tid & 31) == 0) {
                mbar_expect_tx(bar_f2 + 64 * cw + 64, 10240);
                tma_load_3d(sl + 51200, &tmR, layer ? 0 : hg * 80, layer ? hg * 80 : mb * 64, layer ? mb * 2 + cw : cw, bar_f2 + 64 * cw + 64);
            }
            __syncwarp();
            uint32_t pend = 0xffu & ~(1u << hg), v = 0;
            const uint32_t bo = wo_off((tid & 7) + ((tid & 7) < hg)) >> 4, lt = (1u << (tid & 31)) - 1;
#pragma unroll 1
            for (int it = 0; pend && it < 2 * SPIN_MAX; it++) {
                if (v != 4 && (pend >> (tid & 31) & 1)) asm volatile(A1_FLD " %0, [%1];" : "=r"(v) : "l"(fl) : "memory");
                uint32_t fr;
                asm volatile("{\n.reg .pred p;\nmbarrier.test_wait.parity.shared::cta.b64 p, [%1], 0;\nselp.b32 %0, 1, 0, p;\n}" : "=r"(fr) : "r"(bar_e2 + 16 * cw + (tid & 1) * 8) : "memory");
                fr = __ballot_sync(~0u, fr);
                uint32_t m = __ballot_sync(~0u, v == 4 || it >= A1_FSPIN) & pend;
                const int q = 8 - __popc(pend) + __popc(m & lt);
                m &= __ballot_sync(~0u, q < ((fr & 2) ? 8 : (fr & 1) ? 7 : 5));
                pend ^= m;
                if (m >> (tid & 31) & 1) DBGC(12 + cw * 8 + (tid & 7));
                if (!m) __nanosleep(A1_FSLEEP);
                else asm volatile("fence.proxy.async.global;" ::: "memory");
                if (m >> (tid & 31) & 1) {
                    bulk_load(q == 7 && !cw ? sbase + A1_SM_W0 : sl + (q < 6 ? q : q - 6) * 10240, src, 10240, bar_f2 + 64 * cw + 8 * q);
                    asm volatile("st.shared.u32 [%0], %1;" ::"r"(que + 32 * cw + 4 * q), "r"(bo) : "memory");
                    mbar_expect_tx(bar_f2 + 64 * cw + 8 * q, 10240);
                    DBGC(44 + cw * 8 + q);
                }
                __syncwarp();
            }
        }
    } else {
        if (tid == 0) {
            mbar_init(bar_stat, 3);
#pragma unroll
            for (int i = 0; i < 8; i++) mbar_init(bar_kv + 8 * i, 1);
            mbar_init(bars + 144, 1);
            mbar_init(bars + 160, 1);
#pragma unroll
            for (int i = 0; i < 5; i++) mbar_init(bar_rd + 8 * i, 2);
            asm volatile("fence.mbarrier_init.release.cluster;" ::: "memory");
        } else if (tid == 32) {
            mbar_init(bar_wo, 1); mbar_init(bar_done, 3); mbar_init(bar_pv, 4); mbar_init(bar_kvf, 8); mbar_init(bars + 240, 4);
#pragma unroll
            for (int i = 0; i < 4; i++) { mbar_init(bar_e2 + 8 * i, i == 1 ? 2 : 1); mbar_init(bars + 8 * (A1_NST + i), 2); }
            asm volatile("fence.mbarrier_init.release.cluster;" ::: "memory");
        } else if (tid == 64) {
#pragma unroll
            for (int i = 1; i <= 16; i++) mbar_init(bar_f2 + 8 * i, 1);
            asm volatile("fence.mbarrier_init.release.cluster;" ::: "memory");
        }
        asm volatile("bar.sync 0, 384;" ::: "memory");
        SPAN(1 + 4 * layer, 0);
        constexpr int on = 1;
        float acc[120];
        const int lane = tid & 31, warp = w & 7, g = lane >> 2, t = lane & 3;
        if (on) {
            SPAN(1 + 4 * layer, 1);
            TSTAMP1(0);
            if (threadIdx.x == 0) { GSTAMP(g_tim1, 15); }
            TSTAMP3(0);
            if (tid == 0) TSTAMP2(0);
            TSTAMP4(0);
            if (tid == 0) DBGC(60);
            if (layer == 0) a1_mainloop<0>(acc, sbase, bars, wg, tile); else a1_mainloop<1>(acc, sbase, bars, wg, tile);
            uint32_t ok;
            asm volatile("{\n.reg .pred p;\nmbarrier.test_wait.parity.shared::cta.b64 p, [%1], 0;\nselp.b32 %0, 1, 0, p;\n}" : "=r"(ok) : "r"(bar_stat) : "memory");
            if (tid == 128 && !ok) mbar_arrive(bars + 160);
            __syncwarp();
            mbar_wait(bar_stat, 0);
            wgmma_fence();
            wgmma_n240<0, 0>(acc, make_desc(sbase + A1_SM_XA + wg * 1024, 0, 128, 0), make_desc(sbase + A1_SM_XB, 0, 128, 0), 1);
            wgmma_commit();
            if (tid == 128 && ok) mbar_arrive(bars + 160);
            mbar_wait(bars + 8 * (A1_NST + 3), 1);
        }
        const float2* rw = rst + 16 * warp + 8 * wg;
        const float rb0 = rw[g + 8].y, ra = rw[g].y * 0.22360679774997896f, rb = rb0 * 0.22360679774997896f;
        wgmma_wait<0>();
        if ((tid & 127) == 0) mbar_arrive(bar_done);
        TSTAMP1(2);
        TSTAMP1T(13, 224);
        if ((tid & 127) == 0) DBGC(62 - wg);
        uint32_t f[2][30];
#pragma unroll
        for (int j = 10; j < 30; j++) f[1][j] = pack2(acc[4 * j + 2], acc[4 * j + 3]);
        if ((warp & 3) == 3) {
            uint4* hout = g_halo + (((layer * 16 + mb) * 8 + hg) * 2 + wg) * 168;
#pragma unroll
            for (int j = 0; j < 20; j += 4)
                asm volatile("st.relaxed.gpu.global.v4.u32 [%0], {%1,%2,%3,%4};" ::"l"(hout + 8 * j + lane), "r"(f[1][10 + j]), "r"(f[1][11 + j]), "r"(f[1][12 + j]), "r"(f[1][13 + j]) : "memory");
            if (t == 0) asm volatile("st.relaxed.gpu.global.f32 [%0], %1;" ::"l"(reinterpret_cast<float*>(hout + 160) + g), "f"(rb0) : "memory");
        }
        TSTAMP1T(12, 224);
        const uint32_t kvw = sbase + A1_SM_KV + (16 * warp + 8 * wg) * A1_KVP;
        const uint32_t mrow = kvw + (lane & 7) * A1_KVP + (lane >> 3) * 16;
#pragma unroll
        for (int j = 0; j < 20; j += 4) stsm_x4(mrow + 16 * A1_KVP + 16 * j, f[1][10 + j], f[1][11 + j], f[1][12 + j], f[1][13 + j]);
        __syncwarp();
        if (lane == 0 && (warp & 3) != 3) mbar_arrive(bar_kv + 8 * (warp + 1));
#pragma unroll
        for (int j = 0; j < 30; j++) f[0][j] = pack2(acc[4 * j], acc[4 * j + 1]);
        stsm_x4(mrow + 8 * A1_KVP + 160, f[0][20], f[0][21], f[0][22], f[0][23]);
        stsm_x4(mrow + 8 * A1_KVP + 224, f[0][24], f[0][25], f[0][26], f[0][27]);
        asm volatile("stmatrix.sync.aligned.m8n8.x2.shared.b16 [%0], {%1,%2};" ::"r"(mrow + 8 * A1_KVP + 288), "r"(f[0][28]), "r"(f[0][29]) : "memory");
#pragma unroll
        for (int j = 0; j < 10; j++) f[1][j] = pack2(acc[4 * j + 2], acc[4 * j + 3]);
        __syncwarp();
        uint32_t vb[10][2], vp[12], kp[12];
#pragma unroll
        for (int j = 0; j < 10; j += 2) ldsm_x4_t(&vb[j][0], kvw + (8 + (lane & 15)) * A1_KVP + 160 + (lane >> 4) * 16 + 16 * j);
        const bool up0 = 2 * t > g, up1 = 2 * t + 1 > g, edge = (mb | (warp & 3)) == 0;
        float rk[4];
        auto above = [&]() {
            mbar_wait(bar_kv + 8 * warp, 0);
#pragma unroll
            for (int j = 0; j < 12; j += 4) ldsm_x4(&kp[j], mrow + 16 * j);
            rk[0] = rw[2 * t - (up0 ? 8 : 0)].y; rk[1] = rw[2 * t + 1 - (up1 ? 8 : 0)].y;
#pragma unroll
            for (int j = 0; j < 12; j += 4) ldsm_x4_t(&vp[j], mrow + 160 + 16 * j - (j == 8 ? (lane & 16) * 2 : 0));
            __syncwarp();
            if (lane == 0) mbar_arrive(bar_kvf);
        };
        auto halo = [&]() {
            if (lane == 0) mbar_arrive(bar_kvf);
            const uint4* hin = g_halo + (((layer * 16 + mb - 1) * 8 + hg) * 2 + wg) * 168;
            uint32_t hv[22] = {};
            rk[0] = rw[2 * t].y; rk[1] = rw[2 * t + 1].y;
            if (mb > 0) {
#pragma unroll 1
                for (int it = 0; it < SPIN_MAX; it++) {
#pragma unroll
                    for (int k = 0; k < 20; k += 4)
                        asm volatile("ld.relaxed.gpu.global.v4.u32 {%0,%1,%2,%3}, [%4];" : "=r"(hv[k]), "=r"(hv[k + 1]), "=r"(hv[k + 2]), "=r"(hv[k + 3]) : "l"(hin + 8 * k + lane) : "memory");
                    asm volatile("ld.relaxed.gpu.global.v2.u32 {%0,%1}, [%2];" : "=r"(hv[20]), "=r"(hv[21]) : "l"(reinterpret_cast<const uint2*>(hin + 160) + t) : "memory");
                    uint32_t m = max(hv[20], hv[21]);
#pragma unroll
                    for (int k = 0; k < 20; k += 2) m = __vimax3_u32(m, hv[k], hv[k + 1]);
                    if (!__any_sync(~0u, m == ~0u)) break;
                }
            }
            if (tid == 0) mbar_arrive(bars + 144);
            if (lane == 0) DBGC(52 - 16 * wg);
#pragma unroll
            for (int j = 0; j < 10; j++) {
                kp[j] = hv[j];
                asm volatile("movmatrix.sync.aligned.m8n8.trans.b16 %0, %1;" : "=r"(vp[j]) : "r"(hv[10 + j]));
            }
            if (up0) rk[0] = __uint_as_float(hv[20]);
            if (up1) rk[1] = __uint_as_float(hv[21]);
        };
        rk[2] = rw[2 * t + (up0 ? 0 : 8)].y; rk[3] = rw[2 * t + 1 + (up1 ? 0 : 8)].y;
        uint32_t qs[4][2];
#pragma unroll
        for (int h = 0; h < 4; h++) {
            qs[h][0] = (t >> 1) == (h & 1) ? f[0][5 * (h >> 1) + 2] : 0u; qs[h][1] = (t >> 1) == (h & 1) ? f[1][5 * (h >> 1) + 2] : 0u;
            asm volatile("" : "+r"(qs[h][0]), "+r"(qs[h][1]));
        }
#pragma unroll
        for (int j = 0; j < 10; j++) asm volatile("" : "+r"(f[0][j]), "+r"(f[1][j]), "+r"(f[0][10 + j]));
        if (warp & 3) above(); else if (wg) halo();
        TSTAMP1T(10, 64);
        float sc[4][3][4];
#pragma unroll
        for (int h = 0; h < 4; h++) {
            const int jb = 5 * (h >> 1) + 3 * (h & 1), js = 5 * (h >> 1) + 2;
#pragma unroll
            for (int nt = 1; nt < 3; nt++) {
#pragma unroll
                for (int e = 0; e < 4; e++) sc[h][nt][e] = 0.f;
                mma_bf16(sc[h][nt], f[0][jb], f[1][jb], f[0][jb + 1], f[1][jb + 1], f[nt - 1][10 + jb], f[nt - 1][11 + jb]);
                mma_bf16_k8(sc[h][nt], qs[h][0], qs[h][1], f[nt - 1][10 + js]);
            }
        }
        if (tid == 128) mbar_arrive(bars + 240);
        if (warp == 0) halo();
        TSTAMP1(8);
#pragma unroll
        for (int h = 0; h < 4; h++) {
            const int jb = 5 * (h >> 1) + 3 * (h & 1), js = 5 * (h >> 1) + 2;
#pragma unroll
            for (int e = 0; e < 4; e++) sc[h][0][e] = 0.f;
            mma_bf16(sc[h][0], f[0][jb], f[1][jb], f[0][jb + 1], f[1][jb + 1], kp[jb], kp[jb + 1]);
            mma_bf16_k8(sc[h][0], qs[h][0], qs[h][1], kp[js]);
        }
        if (warp > 4) { __syncwarp(); if (lane == 0) mbar_arrive(bars + 240); }
        TSTAMP1T(3, 64);
        float p[4][4], sum[4][2];
        uint32_t lg[4][2], mx[4];
        const float rl[4] = {rk[0] * ra, rk[1] * ra, rk[2] * rb, rk[3] * rb};
        auto max2 = [](uint32_t a, uint32_t b) { uint32_t r; asm("max.bf16x2 %0, %1, %2;" : "=r"(r) : "r"(a), "r"(b)); return r; };
#pragma unroll
        for (int h = 0; h < 4; h++) {
            lg[h][0] = pack2((up0 ? sc[h][0][0] : sc[h][1][0]) * rl[0], (up0 ? sc[h][1][2] : sc[h][2][2]) * rl[2]);
            lg[h][1] = pack2((up1 ? sc[h][0][1] : sc[h][1][1]) * rl[1], (up1 ? sc[h][1][3] : sc[h][2][3]) * rl[3]);
            if (edge) {
                if (up0) lg[h][0] = __byte_perm(lg[h][0], 0xce6eu, 0x3254);
                if (up1) lg[h][1] = __byte_perm(lg[h][1], 0xce6eu, 0x3254);
            }
            mx[h] = max2(lg[h][0], lg[h][1]);
        }
#pragma unroll
        for (int o = 1; o <= 2; o <<= 1)
#pragma unroll
            for (int h = 0; h < 4; h++) mx[h] = max2(mx[h], __shfl_xor_sync(~0u, mx[h], o));
#pragma unroll
        for (int h = 0; h < 4; h++)
#pragma unroll
            for (int r = 0; r < 2; r++) {
                const float m = __uint_as_float(r ? mx[h] & 0xffff0000u : mx[h] << 16);
#pragma unroll
                for (int e = 0; e < 2; e++)
                    asm("ex2.approx.ftz.f32 %0, %1;" : "=f"(p[h][2 * r + e]) : "f"((__uint_as_float(r ? lg[h][e] & 0xffff0000u : lg[h][e] << 16) - m) * 1.4426950408889634f));
                sum[h][r] = p[h][2 * r] + p[h][2 * r + 1];
            }
#pragma unroll
        for (int o = 1; o <= 2; o <<= 1)
#pragma unroll
            for (int h = 0; h < 4; h++)
#pragma unroll
                for (int r = 0; r < 2; r++) sum[h][r] += __shfl_xor_sync(~0u, sum[h][r], o);
        TSTAMP1T(5, 64);
        const uint32_t mu = (up0 ? 0xffffu : 0u) | (up1 ? 0xffff0000u : 0u);
        uint32_t ob[10][2];
#pragma unroll
        for (int P = 0; P < 2; P++) {
            float os[2][4];
#pragma unroll
            for (int e = 0; e < 2; e++) {
                const int h = 2 * P + e;
                const float i0 = rcp_apx(sum[h][0]), i1 = rcp_apx(sum[h][1]);
                const uint32_t w0 = pack2(p[h][0] * rk[0] * i0, p[h][1] * rk[1] * i0), w1 = pack2(p[h][2] * rk[2] * i1, p[h][3] * rk[3] * i1);
#pragma unroll
                for (int dt = 0; dt < 3; dt++) {
                    const int j = 5 * P + (dt < 2 ? 3 * e + dt : 2);
                    float o[4] = {0.f, 0.f, 0.f, 0.f};
                    mma_bf16(o, w0 & ~mu, w1 & mu, 0u, w1 & ~mu, vb[j][0], vb[j][1]);
                    mma_bf16_k8(o, w0 & mu, 0u, vp[j]);
                    if (dt < 2) { ob[j][0] = pack2(o[0], o[1]); ob[j][1] = pack2(o[2], o[3]); }
                    else { os[e][0] = o[0]; os[e][1] = o[1]; os[e][2] = o[2]; os[e][3] = o[3]; }
                }
            }
#pragma unroll
            for (int k = 0; k < 4; k++) os[0][k] = t < 2 ? os[0][k] : os[1][k];
            ob[5 * P + 2][0] = pack2(os[0][0], os[0][1]); ob[5 * P + 2][1] = pack2(os[0][2], os[0][3]);
        }
        const uint32_t sl = sbase + (wg ? A1_SM_A1 : A1_SM_A0);
        const uint32_t o0 = (warp & 3) * 2048 + g * 64 + ((t ^ (g >> 1)) << 4), o1 = 8192 + (warp & 3) * 512 + g * 32 + ((t ^ ((g >> 2) << 1)) << 3);
        mbar_wait(bar_done, 0);
        if (wg == 0) mbar_wait(bar_kvf, 0);
#pragma unroll
        for (int h = 0; h < 2; h++) {
            asm volatile("st.shared.v4.u32 [%0], {%1,%2,%3,%4};" ::"r"(sl + o0 + h * 1024), "r"(ob[0][h]), "r"(ob[1][h]), "r"(ob[2][h]), "r"(ob[3][h]) : "memory");
            asm volatile("st.shared.v4.u32 [%0], {%1,%2,%3,%4};" ::"r"(sl + o0 + h * 1024 + 512), "r"(ob[4][h]), "r"(ob[5][h]), "r"(ob[6][h]), "r"(ob[7][h]) : "memory");
            asm volatile("st.shared.v2.u32 [%0], {%1,%2};" ::"r"(sl + o1 + h * 256), "r"(ob[8][h]), "r"(ob[9][h]) : "memory");
        }
        fence_async_smem();
        __syncwarp();
        TSTAMP1T(4, 64);
        TSTAMP1(1);
        TSTAMP2(1);
        const unsigned char* ot = reinterpret_cast<const unsigned char*>(of) + mb * 163840 + wg * 10240;
        if (lane == 0) {
            asm volatile("cp.async.bulk.global.shared::cta.bulk_group [%0], [%1], 2048;" ::"l"(ot + hg * 20480 + (warp & 3) * 2048), "r"(sl + (warp & 3) * 2048) : "memory");
            asm volatile("cp.async.bulk.global.shared::cta.bulk_group [%0], [%1], 512;" ::"l"(ot + hg * 20480 + 8192 + (warp & 3) * 512), "r"(sl + 8192 + (warp & 3) * 512) : "memory");
            asm volatile("cp.async.bulk.commit_group;" ::: "memory");
            if (wg == 0) mbar_arrive(bar_pv);
            asm volatile("cp.async.bulk.wait_group 0;" ::: "memory");
            asm volatile(A1_FRED " [%0], 1;" ::"l"(reinterpret_cast<uint32_t*>(rsum + 2 * SEQ) + (((layer * 16 + mb) * 2 + wg) * 8 + hg) * FSTR) : "memory");
            DBGC(4 + warp);
        }
        TSTAMP4(11);
        float ac2[40];
        const uint64_t db0 = make_desc(sbase, 1024, 256, 3), db1 = make_desc(sbase + 10240, 512, 256, 3), da0 = make_desc(sl, 16, 1024, 2), da1 = make_desc(sl + 8192, 16, 256, 3);
        const uint32_t o7 = wg ? 640 : (A1_SM_W0 - A1_SM_A0) >> 4;
        const uint32_t trow = ((lane & 7) + 8 * (lane >> 4)) * 128 + (((2 * (warp & 3) + ((lane >> 3) & 1)) ^ (lane & 7)) << 4);
        uint32_t xr[10][2];
        mbar_wait(bar_f2 + 64 * wg + 64, 0);
        if (layer == 0) {
#pragma unroll
            for (int j = 0; j < 10; j += 2) ldsm_x4(&xr[j][0], sl + 51200 + (16 * (warp & 3) + (lane & 15)) * 160 + (lane >> 4) * 16 + 16 * j);
        } else {
#pragma unroll
            for (int j = 0; j < 10; j += 2) ldsm_x4_t(&xr[j][0], sl + 51200 + trow + 1024 * j);
        }
        const uint32_t ri = __shfl_sync(~0u, layer * SEQ + (wg * 2 + ((g >> 1) & 1)) * 512 + (mb * 16 + 4 * (warp & 3) + (g >> 2)) * 2 + (g & 1), lane);
        mbar_wait(bar_wo, 0);
        if (wg) mbar_wait(bar_pv, 0);
        if (wg) asm volatile("bar.sync 2, 128;" ::: "memory"); else asm volatile("bar.sync 1, 128;" ::: "memory");
        TSTAMP2(2);
#pragma unroll
        for (int q = 0; q < 8; q++) {
            uint32_t bo = wo_off(0) >> 4;
            if (q) {
                mbar_wait(bar_f2 + 64 * wg + 8 * q, 0);
                asm volatile("ld.shared.u32 %0, [%1];" : "=r"(bo) : "r"(que + 32 * wg + 4 * q) : "memory");
                bo = __shfl_sync(~0u, bo, 0);
                TSTAMP4(q);
                if (q == 1 && (tid & 127) == 0) DBGC(29 + 8 * wg);
            }
            wgmma_fence();
#pragma unroll
            for (int j = 0; j < 5; j++) wgmma_n80(ac2, (j < 4 ? da0 : da1) + (q == 7 ? o7 : 0u) + (uint64_t)((q < 6 ? q * 640 : 0) + (j & 2) * 16 + (j & 1) * 2), (j < 4 ? db0 : db1) + bo + (uint64_t)((j & 2) * 160 + (j & 1) * 32), j || q);
            wgmma_commit();
            if (q == 0) {
                wgmma_wait<0>();
                if ((tid & 127) == 0) { mbar_arrive(bar_e2 + 16 * wg); mbar_arrive(bar_e2 + 8); }
            }
            if (q == 2 && wg) {
                wgmma_wait<1>();
                if (tid == 128) mbar_arrive(bar_e2 + 24);
            }
        }
        if ((tid & 127) == 0) DBGC(28 + wg * 8 + 7);
        TSTAMP2(3);
        wgmma_wait<0>();
        TSTAMP2(4);
        if (__any_sync(~0u, ac2[0] != ac2[0] || ac2[2] != ac2[2])) {
#pragma unroll
            for (int i = 0; i < 40; i++) ac2[i] = 0.f;
            uint32_t a[20], an[20];
            auto lda = [&](uint32_t (&r)[20], int h) {
#pragma unroll
                for (int u = 0; u < 4; u++)
                    asm volatile("ld.relaxed.gpu.global.v4.u32 {%0,%1,%2,%3}, [%4];" : "=r"(r[4 * u]), "=r"(r[4 * u + 1]), "=r"(r[4 * u + 2]), "=r"(r[4 * u + 3]) : "l"(ot + h * 20480 + o0 + u * 512) : "memory");
#pragma unroll
                for (int u = 0; u < 2; u++)
                    asm volatile("ld.relaxed.gpu.global.v2.u32 {%0,%1}, [%2];" : "=r"(r[16 + 2 * u]), "=r"(r[17 + 2 * u]) : "l"(ot + h * 20480 + o1 + u * 256) : "memory");
            };
            lda(an, 0);
#pragma unroll 5
            for (int k = lane; k < WOB / 16; k += 32)
                reinterpret_cast<uint4*>(stg + (sl - sbase))[k] = __ldcg(reinterpret_cast<const uint4*>(wo + hg * 8 * WOB) + k);
            __syncwarp();
#pragma unroll 1
            for (int h = 0; h < 8; h++) {
#pragma unroll 1
                for (int it = 0; it < SPIN_MAX; it++) {
                    uint32_t m = 0;
#pragma unroll
                    for (int k = 0; k < 20; k += 2) m = __vimax3_u32(m, an[k], an[k + 1]);
                    if (!__any_sync(~0u, m == ~0u)) break;
                    lda(an, h);
                }
#pragma unroll
                for (int k = 0; k < 20; k++) a[k] = an[k];
                lda(an, min(h + 1, 7));
                const uint32_t bp = h == hg ? sl : sbase + wo_off(h + (h < hg));
                const int r0 = 8 * ((lane & 7) >> 1) + 2 * (lane >> 3) + (lane & 1), r2 = 4 * ((lane & 7) >> 1) + 2 * ((lane >> 3) & 1) + (lane & 1);
#pragma unroll
                for (int n = 0; n < 10; n++) {
                    uint32_t b[12];
                    ldsm_x4_t(b, bp + (n >> 1) * 1024 + r0 * 32 + (((n ^ (r0 >> 2)) & 1) << 4));
                    ldsm_x4_t(b + 4, bp + 5120 + (n >> 1) * 1024 + r0 * 32 + (((n ^ (r0 >> 2)) & 1) << 4));
                    ldsm_x4_t(b + 8, bp + 10240 + (n >> 1) * 512 + r2 * 32 + (((n ^ (r2 >> 2)) & 1) << 4));
                    mma_bf16(ac2 + 4 * n, a[0], a[8], a[1], a[9], b[0], b[1]); mma_bf16(ac2 + 4 * n, a[2], a[10], a[3], a[11], b[2], b[3]);
                    mma_bf16(ac2 + 4 * n, a[4], a[12], a[5], a[13], b[4], b[5]); mma_bf16(ac2 + 4 * n, a[6], a[14], a[7], a[15], b[6], b[7]);
                    mma_bf16(ac2 + 4 * n, a[16], a[18], a[17], a[19], b[8], b[9]);
                }
            }
        }
#pragma unroll
        for (int j = 0; j < 10; j++)
#pragma unroll
            for (int hh = 0; hh < 2; hh++) {
                const uint32_t a = pack2(ac2[4 * j + 2 * hh], ac2[4 * j + 2 * hh + 1]);
                const __nv_bfloat162 r = __hadd2_rn(*reinterpret_cast<const __nv_bfloat162*>(&xr[j][hh]), *reinterpret_cast<const __nv_bfloat162*>(&a));
                xr[j][hh] = *reinterpret_cast<const uint32_t*>(&r);
            }
        const uint32_t so = sl + 30720;
#pragma unroll
        for (int j = 0; j < 10; j += 2) stsm_x4_t(so + trow + 1024 * j, xr[j][0], xr[j][1], xr[j + 1][0], xr[j + 1][1]);
        fence_async_smem();
        if (wg) asm volatile("bar.sync 2, 128;" ::: "memory"); else asm volatile("bar.sync 1, 128;" ::: "memory");
        TSTAMP2(5);
        if ((tid & 127) == 0) {
            asm volatile("cp.async.bulk.tensor.2d.global.shared::cta.bulk_group [%0, {%1, %2}], [%3];" ::"l"(&tmX1), "r"(mb * 128 + 64 * wg), "r"(hg * 80), "r"(so) : "memory");
            asm volatile("cp.async.bulk.commit_group;" ::: "memory");
        }
        __syncwarp();
        const float p0 = *(volatile const float*)&rw[g].x, p1 = *(volatile const float*)&rw[g + 8].x;
        float s[3][4] = {};
        const uint32_t pp[2] = {__byte_perm(__float_as_uint(p0), 0, 0x3232), __byte_perm(__float_as_uint(p1), 0, 0x3232)};
#pragma unroll
        for (int j = 0; j < 10; j += 2) {
            const uint32_t d0 = sub2(xr[j][0], pp[0]), d1 = sub2(xr[j][1], pp[1]), d2 = sub2(xr[j + 1][0], pp[0]), d3 = sub2(xr[j + 1][1], pp[1]);
            mma_bf16(s[0], xr[j][0], xr[j][1], xr[j + 1][0], xr[j + 1][1], 0x3f803f80u, 0x3f803f80u);
            mma_bf16(s[1], d0, d1, d2, d3, d0, d2);
            mma_bf16(s[2], d0, d1, d2, d3, d1, d3);
        }
        if (t == (g >> 1)) {
            float2* rp = rsum + ri;
            asm volatile("red.relaxed.gpu.global.add.v2.f32 [%0], {%1, %2};" ::"l"(rp), "f"(fmaf(-80.f, p0, s[0][0])), "f"((g & 1) ? s[1][1] : s[1][0]) : "memory");
            asm volatile("red.relaxed.gpu.global.add.v2.f32 [%0], {%1, %2};" ::"l"(rp + 4), "f"(fmaf(-80.f, p1, s[0][2])), "f"((g & 1) ? s[2][3] : s[2][2]) : "memory");
        }
        asm volatile("cp.async.bulk.wait_group.read 0;" ::: "memory");
        TSTAMP2(6);
        if (tid == 0) DBGC(63);
        if (tid == 128) DBGC(28);
        if (tid == 0) DBGCAL(2);
        GSTAMP(g_tim1, 14);
        SPAN(1 + 4 * layer, 3);
    }
}

static int h_nsm;
static void* h_sym[11];
static TileTab h_tab;
static CUtensorMap h_tmX0, h_tmX1, h_tmR0, h_tmR1, h_tmX1st, h_tmOut, h_tmWq, h_tmWo, h_tmWt, h_tmWc;
typedef CUresult (*PFN_encodeTiled)(CUtensorMap*, CUtensorMapDataType, cuuint32_t, void*, const cuuint64_t*, const cuuint64_t*,
                                    const cuuint32_t*, const cuuint32_t*, CUtensorMapInterleave, CUtensorMapSwizzle,
                                    CUtensorMapL2promotion, CUtensorMapFloatOOBfill);
static void make_tmap(CUtensorMap* tm, const void* ptr, uint64_t cols, uint64_t rows, uint32_t bc, uint32_t br, CUtensorMapSwizzle sw, uint64_t pitch = 0, uint64_t hi = 0, uint32_t bh = 2) {
    static PFN_encodeTiled fn = nullptr;
    if (!fn) {
        void* p = nullptr; cudaDriverEntryPointQueryResult qr;
        cudaGetDriverEntryPoint("cuTensorMapEncodeTiled", &p, cudaEnableDefault, &qr);
        fn = (PFN_encodeTiled)p;
    }
    if (br == 0) {
        cuuint64_t dims[5] = {16, 2, rows / 8, 4, cols / 16}; cuuint64_t strides[4] = {cols * 2, cols * 16, cols * 4, 32};
        cuuint32_t box[5] = {16, 2, bc, 4, 5}; cuuint32_t es[5] = {1, 1, 1, 1, 1};
        fn(tm, CU_TENSOR_MAP_DATA_TYPE_BFLOAT16, 5, const_cast<void*>(ptr), dims, strides, box, es, CU_TENSOR_MAP_INTERLEAVE_NONE, sw,
           CU_TENSOR_MAP_L2_PROMOTION_L2_128B, CU_TENSOR_MAP_FLOAT_OOB_FILL_NONE);
        return;
    }
    if (bh == 0) {
        cuuint64_t dims[5] = {64, 64, 2, 16, 10}; cuuint64_t strides[4] = {pitch * 2, hi * 2, cols * 2, rows * 2};
        cuuint32_t box[5] = {64, 64, 2, 1, 1}; cuuint32_t es[5] = {1, 1, 1, 1, 1};
        fn(tm, CU_TENSOR_MAP_DATA_TYPE_BFLOAT16, 5, const_cast<void*>(ptr), dims, strides, box, es, CU_TENSOR_MAP_INTERLEAVE_NONE, sw,
           CU_TENSOR_MAP_L2_PROMOTION_L2_128B, CU_TENSOR_MAP_FLOAT_OOB_FILL_NONE);
        return;
    }
    if (hi) {
        cuuint64_t dims[3] = {cols, rows, hi == 64 ? 32u : hi == 16 ? 120u : 2u}; cuuint64_t strides[2] = {pitch * 2, hi * 2};
        cuuint32_t box[3] = {bc, br, bh}; cuuint32_t es[3] = {1, 1, 1};
        fn(tm, CU_TENSOR_MAP_DATA_TYPE_BFLOAT16, 3, const_cast<void*>(ptr), dims, strides, box, es, CU_TENSOR_MAP_INTERLEAVE_NONE, sw,
           CU_TENSOR_MAP_L2_PROMOTION_L2_128B, CU_TENSOR_MAP_FLOAT_OOB_FILL_NONE);
        return;
    }
    cuuint64_t dims[2] = {cols, rows}; cuuint64_t strides[1] = {(pitch ? pitch : cols) * 2};
    cuuint32_t box[2] = {bc, br}; cuuint32_t es[2] = {1, 1};
    fn(tm, CU_TENSOR_MAP_DATA_TYPE_BFLOAT16, 2, const_cast<void*>(ptr), dims, strides, box, es, CU_TENSOR_MAP_INTERLEAVE_NONE, sw,
       CU_TENSOR_MAP_L2_PROMOTION_L2_128B, CU_TENSOR_MAP_FLOAT_OOB_FILL_NONE);
}
template <typename... Args>
static void launch_pdl(void (*kern)(Args...), int grid, int block, int smem, Args... args) {
    cudaLaunchConfig_t cfg = {};
    cfg.gridDim = dim3(grid); cfg.blockDim = dim3(block); cfg.dynamicSmemBytes = smem; cfg.stream = cudaStreamPerThread;
    cudaLaunchAttribute at[1];
    at[0].id = cudaLaunchAttributeProgrammaticStreamSerialization; at[0].val.programmaticStreamSerializationAllowed = 1;
    cfg.attrs = at; cfg.numAttrs = 1;
    cudaLaunchKernelEx(&cfg, kern, args...);
}
static void launch_stage(int k, void* const* d_in, void* d_out) {
    const KgIn kg = {(const bf16*)d_in[4], (const bf16*)d_in[5], (const bf16*)d_in[6], (const bf16*)d_in[7], (const bf16*)d_in[8], (const bf16*)d_in[0], (const bf16*)d_in[1], (const bf16*)d_in[2],
                      (uint4*)h_sym[0], (uint4*)h_sym[1], (uint4*)h_sym[2], (uint4*)h_sym[3], (uint4*)h_sym[4], (float*)h_sym[5]};
    switch (k) {
        case 0: kgen_kernel<<<128, 512, KG_SMEM, cudaStreamPerThread>>>(kg, h_tmWq, h_tmWo, h_tmWt, h_tmWc); break;
        case 1: launch_pdl(a1_kernel, h_nsm, A1_THREADS, A1_SMEM, 0, (const bf16*)d_in[0], (const unsigned char*)h_sym[1], (const unsigned char*)h_sym[2], (float2*)h_sym[4], (uint4*)h_sym[6], h_tmX0, h_tmR0, h_tmX1st, h_tab); break;
        case 3: launch_pdl(conv_kernel, DM / CV_CPB, CV_THREADS, CV_SMEM, (const bf16*)d_in[9], 0, (const uint4*)h_sym[7], (const float4*)h_sym[4], (const bf16*)h_sym[8], (bf16*)h_sym[9], (const uint4*)h_sym[0], (bf16*)h_sym[10], h_tmOut); break;
        case 5: launch_pdl(a1_kernel, h_nsm, A1_THREADS, A1_SMEM, 1, (const bf16*)d_in[0], (const unsigned char*)h_sym[1], (const unsigned char*)h_sym[2], (float2*)h_sym[4], (uint4*)h_sym[6], h_tmX1, h_tmR1, h_tmX1st, h_tab); break;
        case 7: launch_pdl(conv_kernel, DM / CV_CPB, CV_THREADS, CV_SMEM, (const bf16*)d_in[9], 1, (const uint4*)h_sym[7] + SEQ / 8, (const float4*)h_sym[4] + SEQ / 2, (const bf16*)h_sym[8], (bf16*)h_sym[10], (const uint4*)h_sym[0], (bf16*)h_sym[10], h_tmOut); break;
        default: break;
    }
}
static int n_stage_kernels() { return 9; }
static const char* stage_name(int k) { const char* n[] = {"kgen", "a1", "a2", "conv", "tr", "a1", "a2", "conv", "tr"}; return n[k]; }

extern "C" void kernel_launch(void* const* d_in, const int* in_sizes, int n_in, void* d_out, int out_size) {
    (void)in_sizes; (void)n_in; (void)out_size;
    static const void *p_in = nullptr, *p_w1 = nullptr, *p_w2 = nullptr, *p_out = nullptr;
    if (p_in != d_in[0] || p_w1 != d_in[1] || p_w2 != d_in[2] || p_out != d_out) {
        cudaFuncSetAttribute(conv_kernel, cudaFuncAttributeMaxDynamicSharedMemorySize, CV_SMEM);
        cudaFuncSetAttribute(kgen_kernel, cudaFuncAttributeMaxDynamicSharedMemorySize, KG_SMEM);
        cudaFuncSetAttribute(a1_kernel, cudaFuncAttributeMaxDynamicSharedMemorySize, A1_SMEM);
        int dev; cudaGetDevice(&dev); cudaDeviceGetAttribute(&h_nsm, cudaDevAttrMultiProcessorCount, dev);
        if (h_nsm != 132) h_nsm = 128;
        h_tab.ns = h_nsm == 132 ? 132 : ~0u;
        for (int i = 0; i < 264; i++) {
            const int h = (i - 64) >> 1;
            const int t = i >= 132 ? i - 132 : i < 64 ? ((i >> 1) & 7) * 16 + (i >> 4) * 2 + (i & 1) : i < 120 ? (1 + h % 7) * 16 + 8 + (h / 7) * 2 + (i & 1) : i < 124 ? 128 : i - 116;
            const int hg = (4 * (t >> 6) + (t & 3)) & 7;
            h_tab.e[i] = {(unsigned char)((t >> 2) & 15), (unsigned char)hg, (unsigned char)(5 * (hg >> 2)), (unsigned char)t, (uint32_t)(hg * 10 * WQ_STAGE)};
        }
        cudaGetSymbolAddress(&h_sym[0], g_tap); cudaGetSymbolAddress(&h_sym[1], g_wq); cudaGetSymbolAddress(&h_sym[2], g_wo);
        cudaGetSymbolAddress(&h_sym[3], g_halo); cudaGetSymbolAddress(&h_sym[4], g_sum); cudaGetSymbolAddress(&h_sym[5], g_csp); cudaGetSymbolAddress(&h_sym[6], g_of);
        cudaGetSymbolAddress(&h_sym[7], g_piv); cudaGetSymbolAddress(&h_sym[8], g_x1T); cudaGetSymbolAddress(&h_sym[9], g_xcT); cudaGetSymbolAddress(&h_sym[10], g_yT);
        void *px1, *px2;
        cudaGetSymbolAddress(&px1, g_x1T); cudaGetSymbolAddress(&px2, g_xcT);
        make_tmap(&h_tmX0, d_in[0], 128 * 640, 64, 64, 64, CU_TENSOR_MAP_SWIZZLE_128B, 1280, 640, 0);
        make_tmap(&h_tmX1, px2, 128, 64 * XCP, 64, 64, CU_TENSOR_MAP_SWIZZLE_128B, XCP, 64, 0);
        make_tmap(&h_tmR0, d_in[0], 640, 1024, 80, 64, CU_TENSOR_MAP_SWIZZLE_NONE, 1280, 640, 1);
        make_tmap(&h_tmR1, px2, 64, 640, 64, 80, CU_TENSOR_MAP_SWIZZLE_128B, XCP, 64, 1);
        make_tmap(&h_tmX1st, px1, 2048, 640, 64, 80, CU_TENSOR_MAP_SWIZZLE_128B, XCP);
        make_tmap(&h_tmWq, d_in[1], 16, 640, 16, 32, CU_TENSOR_MAP_SWIZZLE_32B, 1920, 16, 5);
        make_tmap(&h_tmWc, d_in[1], 16, 640, 16, 64, CU_TENSOR_MAP_SWIZZLE_32B, 1920, 16, 1);
        make_tmap(&h_tmWo, d_in[2], 640, 640, 4, 0, CU_TENSOR_MAP_SWIZZLE_32B);
        make_tmap(&h_tmWt, d_in[2], 640, 640, 2, 0, CU_TENSOR_MAP_SWIZZLE_32B);
        make_tmap(&h_tmOut, d_out, 640, 2048, 80, 8, CU_TENSOR_MAP_SWIZZLE_NONE);
        p_in = d_in[0]; p_w1 = d_in[1]; p_w2 = d_in[2]; p_out = d_out;
    }
    for (int k = 0; k < n_stage_kernels(); k++) launch_stage(k, d_in, d_out);
}
```

```cpp
#include <cuda_runtime.h>
#include <cuda_bf16.h>
#include <stdint.h>
#include <cuda.h>

typedef __nv_bfloat16 bf16;

constexpr int SEQ = 2048;
constexpr int DM = 640;
constexpr int NMODE = 192;

__device__ __forceinline__ float bf2f(bf16 v) { return __bfloat162float(v); }
__device__ __forceinline__ float rbf(float v) {
    uint32_t r;
    asm("cvt.rn.bf16x2.f32 %0, %1, %2;" : "=r"(r) : "f"(v), "f"(0.f));
    return __uint_as_float(r);
}
__device__ __forceinline__ uint32_t pack2(float lo, float hi) {
    __nv_bfloat162 t = __floats2bfloat162_rn(lo, hi);
    return *reinterpret_cast<uint32_t*>(&t);
}
__device__ __forceinline__ void pdl_sync() {
    asm volatile("griddepcontrol.wait;" ::: "memory");
    asm volatile("griddepcontrol.launch_dependents;" ::: "memory");
}
__device__ __forceinline__ float sqrt_apx(float v) { float r; asm("sqrt.approx.ftz.f32 %0, %1;" : "=f"(r) : "f"(v)); return r; }
__device__ __forceinline__ float rcp_apx(float v) { float r; asm("rcp.approx.ftz.f32 %0, %1;" : "=f"(r) : "f"(v)); return r; }
__device__ __forceinline__ uint32_t smem_u32(const void* p) { return (uint32_t)__cvta_generic_to_shared(p); }

constexpr int TPAD = 16;
constexpr int DLEN = 544;
constexpr int TAP_W2 = DLEN * 8, TAP_W3 = TAP_W2 + 768, TAP_C = TAP_W3 + 768, TAPB = TAP_C + 384;
__device__ __align__(128) uint4 g_tap[DM * 128];
#define XPAD 64
constexpr int XCP = SEQ + XPAD;
__device__ __align__(128) bf16 g_x1T[DM * XCP];
__device__ __align__(128) bf16 g_xcT[DM * XCP];
__device__ __align__(128) uint4 g_of[128 * 1280];
constexpr int WQ_STAGE = 240 * 128, WOB = 80 * 160;
__device__ __align__(128) uint4 g_wq[8 * 10 * WQ_STAGE / 16];
__device__ __align__(128) uint4 g_wo[64 * WOB / 16];
__device__ __align__(16) float g_csp[10 * 1920];
#define FSTR 32
__device__ __align__(128) float2 g_sum[2 * SEQ + 256 * FSTR];
__device__ __align__(16) bf16 g_piv[2 * SEQ];
__device__ __align__(128) bf16 g_yT[DM * XCP];
__device__ uint32_t g_epoch;
__device__ __align__(16) unsigned long long g_rstat[SEQ];
__device__ __align__(128) uint4 g_halo[640 * 148];
__device__ __forceinline__ unsigned long long tagw(uint32_t payload, uint32_t tag) { return ((unsigned long long)tag << 32) | payload; }
__device__ __forceinline__ ulonglong2 ld_tag2(const ulonglong2* p) {
    ulonglong2 v;
    asm volatile("ld.relaxed.gpu.global.v2.u64 {%0, %1}, [%2];" : "=l"(v.x), "=l"(v.y) : "l"(p) : "memory");
    return v;
}
__device__ __forceinline__ bool tag_ok(ulonglong2 v, uint32_t tag) { return (uint32_t)(v.x >> 32) == tag && (uint32_t)(v.y >> 32) == tag; }
__device__ __forceinline__ uint32_t ld_epoch() { uint32_t v; asm volatile("ld.relaxed.gpu.global.u32 %0, [%1];" : "=r"(v) : "l"(&g_epoch) : "memory"); return v + 1; }
constexpr int SPIN_MAX = 1 << 20;
__device__ uint32_t g_started[4];
__device__ __forceinline__ void sm_started(int slot) { asm volatile("red.relaxed.gpu.global.add.u32 [%0], 1;" ::"l"(g_started + slot) : "memory"); }
__device__ __noinline__ void sm_idle(int slot) {
    if (threadIdx.x) return;
    sm_started(slot);
    const uint32_t want = ld_epoch() * gridDim.x;
    pdl_sync();
#pragma unroll 1
    for (int it = 0; it < SPIN_MAX; it++) {
        uint32_t v;
        asm volatile("ld.relaxed.gpu.global.u32 %0, [%1];" : "=r"(v) : "l"(g_started + slot) : "memory");
        if ((int)(v - want) >= 0) break;
        __nanosleep(100);
    }
}
struct TileTab { uint32_t ns, pad; struct { unsigned char mb, hg, kb0, tile; uint32_t woff; } __align__(8) e[264]; };
__device__ __forceinline__ bool elect() {
    uint32_t p;
    asm volatile("{\n.reg .pred p;\nelect.sync _|p, 0xffffffff;\nselp.b32 %0, 1, 0, p;\n}" : "=r"(p));
    return p;
}
#define DBG_SYMS
#define TSTAMP(i)
#define TSTAMP1(i)
#define TSTAMP1T(i, t)
#define TSTAMP1X(i, t)
#define SPAN(k, i)
#define GSTAMP(arr, i)
#define TSTAMP2(i)
#define TSTAMP3(i)
#define TSTAMP4(i)
#define TSTAMPK(i, t)
#define DBGC(i)
#define DBGV(i, v)
#define DBGCAL(i)

__device__ __forceinline__ void mma_bf16(float* d, uint32_t a0, uint32_t a1, uint32_t a2, uint32_t a3, uint32_t b0, uint32_t b1) {
    asm volatile("mma.sync.aligned.m16n8k16.row.col.f32.bf16.bf16.f32 {%0,%1,%2,%3}, {%4,%5,%6,%7}, {%8,%9}, {%0,%1,%2,%3};"
                 : "+f"(d[0]), "+f"(d[1]), "+f"(d[2]), "+f"(d[3]) : "r"(a0), "r"(a1), "r"(a2), "r"(a3), "r"(b0), "r"(b1));
}
__device__ __forceinline__ void mma_bf16_k8(float* d, uint32_t a0, uint32_t a1, uint32_t b0) {
    asm volatile("mma.sync.aligned.m16n8k8.row.col.f32.bf16.bf16.f32 {%0,%1,%2,%3}, {%4,%5}, {%6}, {%0,%1,%2,%3};"
                 : "+f"(d[0]), "+f"(d[1]), "+f"(d[2]), "+f"(d[3]) : "r"(a0), "r"(a1), "r"(b0));
}
__device__ __forceinline__ void ldsm_x4(uint32_t* r, uint32_t addr) {
    asm volatile("ldmatrix.sync.aligned.m8n8.x4.shared.b16 {%0,%1,%2,%3}, [%4];"
                 : "=r"(r[0]), "=r"(r[1]), "=r"(r[2]), "=r"(r[3]) : "r"(addr));
}

__device__ __forceinline__ void ldsm_x4_t(uint32_t* r, uint32_t addr) {
    asm volatile("ldmatrix.sync.aligned.m8n8.x4.trans.shared.b16 {%0,%1,%2,%3}, [%4];"
                 : "=r"(r[0]), "=r"(r[1]), "=r"(r[2]), "=r"(r[3]) : "r"(addr));
}
__device__ __forceinline__ void mbar_init(uint32_t bar, int count) { asm volatile("mbarrier.init.shared::cta.b64 [%0], %1;" ::"r"(bar), "r"(count)); }
__device__ __forceinline__ void mbar_arrive(uint32_t bar) { asm volatile("mbarrier.arrive.shared::cta.b64 _, [%0];" ::"r"(bar) : "memory"); }
__device__ __forceinline__ void mbar_wait(uint32_t bar, uint32_t parity) {
    asm volatile("{\n.reg .pred p;\nWAIT_LOOP:\n"
                 "mbarrier.try_wait.parity.shared::cta.b64 p, [%0], %1;\n"
                 "@p bra.uni WAIT_DONE;\nbra.uni WAIT_LOOP;\nWAIT_DONE:\n}" ::"r"(bar), "r"(parity) : "memory");
}

__device__ __forceinline__ void mbar_expect_tx(uint32_t bar, uint32_t bytes) {
    asm volatile("mbarrier.arrive.expect_tx.shared::cta.b64 _, [%0], %1;" ::"r"(bar), "r"(bytes) : "memory");
}
__device__ __forceinline__ void tma_load_2d(uint32_t dst, const void* tmap, int c0, int c1, uint32_t bar) {
    asm volatile("cp.async.bulk.tensor.2d.shared::cluster.global.mbarrier::complete_tx::bytes [%0], [%1, {%3, %4}], [%2];"
                 ::"r"(dst), "l"(tmap), "r"(bar), "r"(c0), "r"(c1) : "memory");
}
__device__ __forceinline__ void tma_load_3d(uint32_t dst, const void* tmap, int c0, int c1, int c2, uint32_t bar) {
    asm volatile("cp.async.bulk.tensor.3d.shared::cluster.global.mbarrier::complete_tx::bytes [%0], [%1, {%3, %4, %5}], [%2];"
                 ::"r"(dst), "l"(tmap), "r"(bar), "r"(c0), "r"(c1), "r"(c2) : "memory");
}
__device__ __forceinline__ void fence_async_smem() { asm volatile("fence.proxy.async.shared::cta;" ::: "memory"); }
__device__ __forceinline__ void bulk_load(uint32_t dst, const void* src, uint32_t bytes, uint32_t bar) {
    asm volatile("cp.async.bulk.shared::cluster.global.mbarrier::complete_tx::bytes [%0], [%1], %2, [%3];"
                 ::"r"(dst), "l"(src), "r"(bytes), "r"(bar) : "memory");
}
__device__ __forceinline__ void tma_store_2d(const void* tmap, int c0, int c1, uint32_t src) {
    asm volatile("cp.async.bulk.tensor.2d.global.shared::cta.bulk_group [%0, {%1, %2}], [%3];" ::"l"(tmap), "r"(c0), "r"(c1), "r"(src) : "memory");
    asm volatile("cp.async.bulk.commit_group;" ::: "memory");
    asm volatile("cp.async.bulk.wait_group.read 0;" ::: "memory");
}
__device__ __forceinline__ void stsm_x4(uint32_t addr, uint32_t r0, uint32_t r1, uint32_t r2, uint32_t r3) {
    asm volatile("stmatrix.sync.aligned.m8n8.x4.shared.b16 [%0], {%1,%2,%3,%4};" ::"r"(addr), "r"(r0), "r"(r1), "r"(r2), "r"(r3) : "memory");
}
__device__ __forceinline__ void stsm_x4_t(uint32_t addr, uint32_t r0, uint32_t r1, uint32_t r2, uint32_t r3) {
    asm volatile("stmatrix.sync.aligned.m8n8.x4.trans.shared.b16 [%0], {%1,%2,%3,%4};" ::"r"(addr), "r"(r0), "r"(r1), "r"(r2), "r"(r3) : "memory");
}
__device__ __forceinline__ void prefetch_tmap(const void* tmap) { asm volatile("prefetch.tensormap [%0];" ::"l"(tmap) : "memory"); }

__device__ __forceinline__ float2 cexp_at(float wr2, float wi, float p) {
    float er;
    asm("ex2.approx.ftz.f32 %0, %1;" : "=f"(er) : "f"(wr2 * p));
    float th = wi * p;
    const float k = rintf(th * 0.15915494309189535f);
    th = fmaf(k, -6.2831854820251465f, th);
    th = fmaf(k, 1.7484555314695172e-7f, th);
    return make_float2(er * __cosf(th), er * __sinf(th));
}
__device__ __forceinline__ float2 cmul(float2 a, float2 b) {
    return make_float2(fmaf(a.x, b.x, -a.y * b.y), fmaf(a.x, b.y, a.y * b.x));
}
__device__ __forceinline__ float2 csqr(float2 a) { return make_float2(fmaf(a.x, a.x, -a.y * a.y), (a.x + a.x) * a.y); }
__device__ __forceinline__ uint32_t packh(float2 v) {
    uint32_t r;
    asm("cvt.rn.f16x2.f32 %0, %1, %2;" : "=r"(r) : "f"(v.y), "f"(v.x));
    return r;
}
__device__ __forceinline__ void mma_f16(float* d, uint32_t a0, uint32_t a1, uint32_t a2, uint32_t a3, uint32_t b0, uint32_t b1) {
    asm volatile("mma.sync.aligned.m16n8k16.row.col.f32.f16.f16.f32 {%0,%1,%2,%3}, {%4,%5,%6,%7}, {%8,%9}, {%0,%1,%2,%3};"
                 : "+f"(d[0]), "+f"(d[1]), "+f"(d[2]), "+f"(d[3]) : "r"(a0), "r"(a1), "r"(a2), "r"(a3), "r"(b0), "r"(b1));
}

struct KgIn { const bf16 *logA, *Aim, *Cre, *Cim, *logdt, *x, *wqkv, *wo; uint4 *tap, *wq, *wop, *halo, *sum; float* csp; };
constexpr int KG_THREADS = NMODE / 2;

constexpr int KG_SMEM = 15 * 14336 + 3 * 5120 + 192;
__global__ void __launch_bounds__(512, 1) kgen_kernel(const KgIn in, const __grid_constant__ CUtensorMap tmWq, const __grid_constant__ CUtensorMap tmWo,
                                                        const __grid_constant__ CUtensorMap tmWt, const __grid_constant__ CUtensorMap tmWc) {
    extern __shared__ __align__(1024) uint4 tabs[];
#define KG_CS 1
#define KG_ROT 0
    const int lane = threadIdx.x & 31, w16 = (__shfl_sync(~0u, threadIdx.x >> 5, 0) + KG_ROT) & 15, grp = w16 / 3, warp = w16 - 3 * grp;
    const int d = blockIdx.x * 5 + grp, tid = warp * 32 + lane;
    uint4* tab = tabs + grp * (3 * 896);
    SPAN(0, 0); SPAN(0, 1);
    TSTAMPK(0, 0);
    asm volatile("griddepcontrol.launch_dependents;" ::: "memory");
    if (w16 == 15) {
        const uint32_t b0 = smem_u32(tab), wbar = b0 + 3 * 5120;
        const int blk = blockIdx.x, nq = blk < 112 ? 4 : 2, nj = nq + (blk < 64 ? 1 : 2);
        auto fetch = [&](int i) {
            const uint32_t dst = b0 + (i % 3) * 5120, bar = wbar + 8 * i;
            if (i < nq) {
                const int p = blk + 64 * (i & 2), kb = p / 24;
                mbar_expect_tx(bar, 5120);
                tma_load_3d(dst, &tmWq, 0, kb * 64 + (i & 1) * 32, (p - 24 * kb) * 5, bar);
            } else if (i < nj) {
                const int o = i == nq ? blk : 255 - blk;
                mbar_expect_tx(bar, o < 128 ? 5120 : 2560);
                asm volatile("cp.async.bulk.tensor.5d.shared::cluster.global.mbarrier::complete_tx::bytes [%0], [%1, {%3, %3, %4, %3, %5}], [%2];"
                             ::"r"(dst), "l"(o < 128 ? &tmWo : &tmWt), "r"(bar), "r"(0), "r"((o & 7) * 10 + (o >> 6) * 4), "r"(((o >> 3) & 7) * 5) : "memory");
            }
        };
        if (elect()) {
#pragma unroll
            for (int i = 0; i < 6; i++) mbar_init(wbar + 8 * i, 1);
            asm volatile("fence.mbarrier_init.release.cluster;" ::: "memory");
#pragma unroll
            for (int i = 0; i < 3; i++) fetch(i);
            prefetch_tmap(&tmWo); prefetch_tmap(&tmWt); prefetch_tmap(&tmWc);
#pragma unroll 1
            for (int i = 0; i < nj; i++) {
                const int p = blk + 64 * (i & 2), kb = p / 24, hg = p & 7, sec = (p - 24 * kb) >> 3, o = i == nq ? blk : 255 - blk, cg = (o >> 3) & 7, hb = o & 7;
                const unsigned char* dst = i < nq ? reinterpret_cast<unsigned char*>(in.wq) + (hg * 10 + (hg < 4 ? kb : kb < 5 ? kb + 5 : kb - 5)) * WQ_STAGE + ((i & 1) * 3 + sec) * 5120
                                                  : reinterpret_cast<unsigned char*>(in.wop) + (cg * 8 + (hb == cg ? 0 : hb + (hb < cg))) * WOB + (o >> 6) * 5120;
                mbar_wait(wbar + 8 * i, 0);
                if (i == 0) TSTAMPK(2, (15 - KG_ROT) * 32);
                if (i == 3) TSTAMPK(5, (15 - KG_ROT) * 32);
                asm volatile("cp.async.bulk.global.shared::cta.bulk_group [%0], [%1], %2;" ::"l"(dst), "r"(b0 + (i % 3) * 5120), "r"(i < nq || o < 128 ? 5120 : 2560) : "memory");
                asm volatile("cp.async.bulk.commit_group;" ::: "memory");
                if (i == 2) {
                    asm volatile("cp.async.bulk.wait_group.read 0;" ::: "memory");
                    TSTAMPK(3, (15 - KG_ROT) * 32);
#pragma unroll 1
                    for (int k = 3; k < 6; k++) fetch(k);
                }
            }
            asm volatile("cp.async.bulk.wait_group.read 0;" ::: "memory");
        }
        TSTAMPK(11, (15 - KG_ROT) * 32);
        return;
    }
    const bf16 pdt = in.logdt[d];
    const uint32_t pla = reinterpret_cast<const uint32_t*>(in.logA)[d * KG_THREADS + tid], pai = reinterpret_cast<const uint32_t*>(in.Aim)[d * KG_THREADS + tid];
    const uint32_t pcr = reinterpret_cast<const uint32_t*>(in.Cre)[d * KG_THREADS + tid], pci = reinterpret_cast<const uint32_t*>(in.Cim)[d * KG_THREADS + tid];
    const bf16* pfq = tid < 30 ? in.wqkv + (size_t)(d * 30 + tid) * 64 : tid < 40 ? in.wo + (size_t)(d * 10 + tid - 30) * 64 : in.x + (size_t)(d * 32 + tid - 40) * 64;
#define KG_PF 0
    if (tid < (KG_PF == 3 ? 0 : KG_PF ? 40 : 72)) asm volatile("prefetch.global.L2 [%0];" ::"l"(pfq));
    asm volatile("st.global.v4.u32 [%0], {%1,%1,%1,%1};" ::"l"(in.halo + d * 148 + tid), "r"(~0u));
    if (tid < 52) asm volatile("st.global.v4.u32 [%0], {%1,%1,%1,%1};" ::"l"(in.halo + d * 148 + 96 + tid), "r"(~0u));
    else if (w16 == 2) {
        if (lane < 16) in.sum[blockIdx.x * 16 + lane] = make_uint4(0, 0, 0, 0);
        else if (lane < 20) reinterpret_cast<uint32_t*>(in.sum + 2048)[(blockIdx.x * 4 + lane - 16) * FSTR] = 0;
    }
    const uint32_t tw = smem_u32(tab) + warp * 14336, cbar = smem_u32(tabs) + 15 * 14336 + 3 * 5120 + 64 + 8 * w16;
    if (lane == 0) { mbar_init(cbar, 1); mbar_expect_tx(cbar, 2048); }
    const int g = lane >> 2, t = lane & 3;
    const uint32_t sta = tw + lane * 128 + ((2 * (lane & 3) + ((lane >> 2) & 1)) << 4);
    const uint32_t lda = tw + t * 128 + ((g ^ (2 * t)) << 4);
    const uint32_t stb = tw + 12288 + lane * 64 + ((4 * ((lane >> 1) & 1) + ((lane >> 2) & 3)) << 3);
    const uint32_t ldb = tw + 12288 + t * 64 + ((g ^ (4 * (t >> 1))) << 3);
    auto sts4 = [&](int e, int off, uint32_t a, uint32_t b, uint32_t c, uint32_t dd) {
        asm volatile("st.shared.v4.u32 [%0], {%1,%2,%3,%4};" ::"r"((sta ^ (e << 4)) + off), "r"(a), "r"(b), "r"(c), "r"(dd) : "memory");
    };
    auto lds4 = [&](int sp, int off, uint32_t* r) {
        asm volatile("ld.shared.v4.u32 {%0,%1,%2,%3}, [%4];" : "=r"(r[0]), "=r"(r[1]), "=r"(r[2]), "=r"(r[3]) : "r"((lda ^ ((sp & 1) << 4)) + sp * 512 + off) : "memory");
    };
    const float dt = rbf(expf(bf2f(pdt)));
    float2 C[2], y1[2], z8[2], y128[2];
    float cmax = 0.f;
#pragma unroll
    for (int m = 0; m < 2; m++) {
        const float wr2 = -rbf(expf(__uint_as_float(m ? pla & 0xffff0000u : pla << 16))) * dt * 1.4426950408889634f;
        const float wi = __uint_as_float(m ? pai & 0xffff0000u : pai << 16) * dt;
        C[m] = make_float2(__uint_as_float(m ? pcr & 0xffff0000u : pcr << 16) * dt, -__uint_as_float(m ? pci & 0xffff0000u : pci << 16) * dt);
        cmax = fmaxf(cmax, fmaxf(fabsf(C[m].x), fabsf(C[m].y)));
        y1[m] = cexp_at(wr2, -wi, 1.f); z8[m] = cexp_at(wr2, wi, 8.f); y128[m] = cexp_at(wr2, -wi, 128.f);
    }
    const int ex = min(max((int)(__reduce_max_sync(~0u, __float_as_uint(cmax)) >> 23), 20), 240);
    const float scale = __uint_as_float((uint32_t)(127 + 10 + 127 - ex) << 23), unscale = 2.0f * __uint_as_float((uint32_t)(ex - 10) << 23);
    TSTAMPK(4, 64);
    if (KG_PF >= 2 && tid >= 40 && tid < 72) asm volatile("prefetch.global.L2 [%0];" ::"l"(pfq));
    float k2048 = 0.f;
    float acc[5][4];
#pragma unroll
    for (int j = 0; j < 5; j++)
#pragma unroll
        for (int k = 0; k < 4; k++) acc[j][k] = 0.f;
    uint32_t af[8][4];
    {
        float2 h0[2], h1[2], g0[2], g1[2], g2[2], g2b[2], g3[2], g4[2], y2[2], y4[2];
#pragma unroll
        for (int m = 0; m < 2; m++) {
            h0[m] = make_float2(1.f, 0.f); h1[m] = csqr(csqr(csqr(z8[m])));
            g0[m] = make_float2(C[m].x * scale, C[m].y * scale);
            g1[m] = cmul(g0[m], y128[m]);
            const float2 y256 = csqr(y128[m]), y512 = csqr(y256);
            g2b[m] = g2[m] = cmul(g0[m], y256); g3[m] = cmul(g0[m], y512); g4[m] = cmul(g3[m], y512);
            y2[m] = csqr(y1[m]); y4[m] = csqr(y2[m]);
            const float2 y1024 = csqr(y512);
            k2048 += fmaf(g4[m].x, y1024.x, -g4[m].y * y1024.y);
        }
#pragma unroll
        for (int e = 0; e < 8; e++) {
            sts4(e, 0, packh(h0[0]), packh(h1[0]), packh(h0[1]), packh(h1[1]));
            sts4(e, 4096, packh(g0[0]), packh(g0[1]), packh(g1[0]), packh(g1[1]));
#pragma unroll
            for (int m = 0; m < 2; m++)
                if (e < 7) { h0[m] = e ? cmul(h0[m], z8[m]) : z8[m]; h1[m] = cmul(h1[m], z8[m]); g0[m] = cmul(g0[m], y1[m]); g1[m] = cmul(g1[m], y1[m]); }
            if (e < 5) k2048 += __shfl_xor_sync(~0u, k2048, 1 << e);
        }
        if (KG_PF == 1 && tid >= 40 && tid < 72) asm volatile("prefetch.global.L2 [%0];" ::"l"(pfq));
        __syncwarp();
#pragma unroll
        for (int e = 0; e < 8; e++) {
            uint32_t b[4];
            lds4(e, 0, af[e]); lds4(e, 4096, b);
            sts4(e, 8192, packh(g2[0]), packh(g2[1]), packh((e & 1) ? cmul(g3[0], y4[0]) : g3[0]), packh((e & 1) ? cmul(g3[1], y4[1]) : g3[1]));
            asm volatile("st.shared.v2.u32 [%0], {%1,%2};" ::"r"(stb ^ (e << 3)), "r"(packh(g4[0])), "r"(packh(g4[1])) : "memory");
#pragma unroll
            for (int m = 0; m < 2; m++)
                if (e < 7) {
                    g2[m] = e == 3 ? cmul(g2b[m], y128[m]) : cmul(g2[m], y2[m]);
                    if (e & 1) g3[m] = cmul(g3[m], y128[m]);
                    g4[m] = cmul(g4[m], y128[m]);
                }
            mma_f16(acc[0], af[e][0], af[e][1], af[e][2], af[e][3], b[0], b[1]);
            mma_f16(acc[1], af[e][0], af[e][1], af[e][2], af[e][3], b[2], b[3]);
        }
    }
    TSTAMPK(6, 64);
    const int job = w16 * 128 + blockIdx.x, skb = job / 120, sa = job - 120 * skb;
    __syncwarp();
    if (job < 1200 && elect()) tma_load_3d(tw + 4096, &tmWc, 0, skb * 64, sa, cbar);
#pragma unroll
    for (int sp = 0; sp < 8; sp++) {
        uint32_t c[4], e0, e1;
        lds4(sp, 8192, c);
        asm volatile("ld.shared.v2.u32 {%0,%1}, [%2];" : "=r"(e0), "=r"(e1) : "r"((ldb ^ ((sp & 3) << 3)) + sp * 256) : "memory");
        mma_f16(acc[2], af[sp][0], af[sp][1], af[sp][2], af[sp][3], c[0], c[1]);
        mma_f16(acc[3], af[sp][0], af[sp][1], af[sp][2], af[sp][3], c[2], c[3]);
        mma_f16(acc[4], af[sp][0], af[sp][1], af[sp][2], af[sp][3], e0, e1);
    }
    {
        float* Pp = reinterpret_cast<float*>(tab + warp * 896);
#pragma unroll
        for (int h = 0; h < 2; h++) {
            const int b = g + 8 * h;
            *reinterpret_cast<float2*>(Pp + 8 * b + 2 * t) = make_float2(acc[0][2 * h] * unscale, acc[0][2 * h + 1] * unscale);
            *reinterpret_cast<float2*>(Pp + 128 + 8 * b + 2 * t) = make_float2(acc[1][2 * h] * unscale, acc[1][2 * h + 1] * unscale);
            *reinterpret_cast<float2*>(Pp + 256 + 4 * b + 2 * (t & 1) + 64 * (t >> 1)) = make_float2(acc[2][2 * h] * unscale, acc[2][2 * h + 1] * unscale);
            *reinterpret_cast<float2*>(Pp + 384 + 2 * b + 32 * t) = make_float2(acc[3][2 * h] * unscale, acc[3][2 * h + 1] * unscale);
            Pp[512 + b + 32 * t] = acc[4][2 * h] * unscale;
            Pp[512 + b + 32 * t + 16] = acc[4][2 * h + 1] * unscale;
        }
        if (lane == 0) Pp[640] = k2048 * unscale;
    }
    TSTAMPK(7, 64);
    asm volatile("bar.sync %0, 96;" ::"r"(grp + 1) : "memory");
    TSTAMPK(9, 64);
    const float* Kp = reinterpret_cast<const float*>(tab);
    auto ksum = [&](int i) -> float { return (Kp[i] + Kp[3584 + i]) + Kp[7168 + i]; };
    auto ksum4 = [&](int q) -> float4 {
        const float4 a = reinterpret_cast<const float4*>(Kp)[q], b = reinterpret_cast<const float4*>(Kp)[896 + q], c = reinterpret_cast<const float4*>(Kp)[1792 + q];
        return make_float4((a.x + b.x) + c.x, (a.y + b.y) + c.y, (a.z + b.z) + c.z, (a.w + b.w) + c.w);
    };
    {
        uint2* E4 = reinterpret_cast<uint2*>(in.tap + d * 128);
        float4 v = ksum4(tid), u = ksum4(96 + min(tid, 64));
        const float cor = rbf(ksum(tid == 95 ? 384 : 512));
        if (tid == 95) v.w -= cor;
        if (tid == 31) u.w -= cor;
        const uint32_t lo = pack2(v.x, v.y), hi = pack2(v.z, v.w);
        if (tid < 64) {
            E4[6 + tid] = make_uint2(lo, hi);
            E4[(tid < 32 ? 159 : 209 - 32) + tid] = make_uint2(pack2(u.x, u.y), pack2(u.z, u.w));
        } else {
            const uint32_t nx = __shfl_down_sync(~0u, lo, 1);
            in.tap[d * 128 + 35 + tid - 64] = make_uint4(__byte_perm(lo, 0, 0x1010), __byte_perm(lo, hi, 0x5432), __byte_perm(hi, 0, 0x1010), __byte_perm(hi, tid == 95 ? 0u : nx, 0x5432));
            if (tid == 64) E4[241] = make_uint2(pack2(u.x, 0.f), 0u);
        }
    }
    TSTAMPK(10, 64);
    if (job < 1200) {
        mbar_wait(cbar, 0);
        uint32_t w[4][4];
        float cs[4] = {0.f, 0.f, 0.f, 0.f};
#pragma unroll
        for (int a = 0; a < 4; a++) ldsm_x4_t(w[a], tw + 4096 + ((lane >> 4) * 8 + (lane & 7)) * 32 + ((((lane >> 3) ^ (lane >> 2)) & 1) << 4) + a * 512);
#pragma unroll
        for (int a = 0; a < 4; a++) mma_bf16(cs, w[a][0], w[a][1], w[a][2], w[a][3], 0x3f803f80u, 0x3f803f80u);
        if (t < 2) in.csp[skb * 1920 + sa * 16 + g + 8 * t] = t ? cs[2] : cs[0];
    }
    SPAN(0, 3);
}

#define CV_MODE 0
#define CV_LD __ldcg
#define CV_LDX __ldcg
#define CV_SLEEP 100
constexpr int CV_CPB = 5;
constexpr int CV_THREADS = 512;
constexpr int UPADF = 128;
constexpr int ULEN = UPADF + SEQ + 80;
constexpr int XLEN = SEQ + 16;
constexpr int BX_5 = 0, BX_3 = 3264, BX_9 = 6528, BX_7 = 8960, BX_LEN = 11392;
constexpr int CV_SM_T = 0;
constexpr int CV_SM_B = CV_CPB * TAPB;
constexpr int CV_SM_U = CV_SM_B + CV_CPB * BX_LEN;
constexpr int CV_SM_X = CV_SM_U + CV_CPB * ULEN * 2;
constexpr int CV_SM_Y = CV_SM_X + CV_CPB * XLEN * 2;
constexpr int CV_SM_P = CV_SM_Y + CV_CPB * XLEN * 2;
constexpr int CV_SM_CNT = CV_SM_P + 6 * 4096;
constexpr int CV_SM_O = (CV_SM_CNT + 128 + 127) & ~127;
constexpr int CV_SMEM = CV_SM_O + 20480;
static_assert(CV_SM_B % 128 == 0 && CV_SM_CNT % 16 == 0, "layout");

__device__ __forceinline__ uint32_t sub2(uint32_t x, uint32_t m) {
    const __nv_bfloat162 d = __hsub2(*reinterpret_cast<const __nv_bfloat162*>(&x), *reinterpret_cast<const __nv_bfloat162*>(&m));
    return *reinterpret_cast<const uint32_t*>(&d);
}
__device__ __forceinline__ uint32_t add2(uint32_t x, uint32_t y) {
    const __nv_bfloat162 d = __hadd2_rn(*reinterpret_cast<const __nv_bfloat162*>(&x), *reinterpret_cast<const __nv_bfloat162*>(&y));
    return *reinterpret_cast<const uint32_t*>(&d);
}
__device__ __forceinline__ void cp_async16(uint32_t dst, const void* src) {
    asm volatile("cp.async.cg.shared.global [%0], [%1], 16;" ::"r"(dst), "l"(src));
}
__device__ __forceinline__ void cp_async_wait_all() { asm volatile("cp.async.wait_all;" ::: "memory"); }

template <bool FULL>
__device__ __forceinline__ void direct_pass(float (&acc)[8][4], uint32_t ub, uint32_t o0, uint32_t o1, const uint2* __restrict__ Tp, bool first_half) {
    uint32_t sw[8][8];
#pragma unroll
    for (int j = 0; j < 8; j++) { ldsm_x4(&sw[j][0], ub + o0 + j * 256); ldsm_x4(&sw[j][4], ub + o1 + j * 256); }
#pragma unroll
    for (int M = 0; M < 4; M++) {
#pragma unroll
        for (int i = 0; i < 4; i++) {
            const uint2 hi = Tp[128 * M + 16 * i], lo = Tp[128 * M + 16 * i - 8];
#pragma unroll
            for (int j = FULL ? 0 : M; j < 8; j++) mma_bf16(acc[j], hi.x, hi.y, lo.x, lo.y, sw[(j - M) & 7][2 * i], sw[(j - M) & 7][2 * i + 1]);
        }
        if (FULL) {
            ldsm_x4(&sw[7 - M][0], ub + o0 - (M + 1) * 256);
            if (M < 3) ldsm_x4(&sw[7 - M][4], ub + o1 - (M + 1) * 256);
        }
    }
    if (first_half) {
        const uint2 hi = Tp[512], lo = Tp[504];
#pragma unroll
        for (int j = FULL ? 0 : 4; j < 8; j++) mma_bf16(acc[j], hi.x, hi.y, lo.x, lo.y, sw[(j - 4) & 7][0], sw[(j - 4) & 7][1]);
    }
}
__device__ __forceinline__ uint32_t fin2(uint32_t y, uint32_t u, uint32_t dk) {
    typedef __nv_bfloat162 b2;
    const b2 r = __hadd2_rn(*reinterpret_cast<const b2*>(&y), __hmul2_rn(*reinterpret_cast<const b2*>(&u), *reinterpret_cast<const b2*>(&dk)));
    return *reinterpret_cast<const uint32_t*>(&r);
}
__global__ void __launch_bounds__(CV_THREADS, 1) conv_kernel(const bf16* __restrict__ Dskip, int layer, const uint4* __restrict__ piv, const float4* __restrict__ sum, const bf16* __restrict__ x1T,
                                                             bf16* __restrict__ dst, const uint4* __restrict__ tap, bf16* __restrict__ yT, const __grid_constant__ CUtensorMap tmOut) {
    extern __shared__ __align__(128) unsigned char sm[];
    SPAN(3 + 4 * layer, 0);
    bf16* Us = reinterpret_cast<bf16*>(sm + CV_SM_U);
    bf16* Xs = reinterpret_cast<bf16*>(sm + CV_SM_X);
    bf16* Ys = reinterpret_cast<bf16*>(sm + CV_SM_Y);
    const int tid = threadIdx.x, lane = tid & 31, warp = __shfl_sync(~0u, tid >> 5, 0);
    const int d0 = blockIdx.x * CV_CPB, tile = blockIdx.x; (void)tile;
    const int g = lane >> 2, ti = lane & 3;
    const int e = g - 2 * ti;
    uint32_t lds_off[4];
    uint32_t off2, off3, offc;
    {
        const int mat = lane >> 3, r = lane & 7;
#pragma unroll
        for (int pr = 0; pr < 4; pr++) {
            const int iw = 2 * pr + (mat >> 1), half = mat & 1;
            const int chunk = (UPADF - 16 * iw + 16 * r + 8 * half) >> 3;
            lds_off[pr] = (uint32_t)((chunk ^ ((chunk >> 3) & 1)) * 16);
        }
        const int j2 = 13 + r + 8 * (mat >> 1), j3 = j2 + 2, i0 = 8 * (mat & 1);
        off2 = (j2 & 1) ? BX_3 + (4 * j2 + i0 + 84) * 2 : BX_5 + (4 * j2 + i0 + 80) * 2;
        off3 = ((j3 & 1) ? BX_7 : BX_9) + (8 * j3 + i0 + 136) * 2;
        const int cc = (UPADF + 16 * (r + (mat >> 1)) + i0) >> 3;
        offc = (uint32_t)((cc ^ ((cc >> 3) & 1)) * 16);
    }
#define CV_WX 0
    const int wv = warp ^ CV_WX;
    const uint32_t rtab = wv < 8 ? (wv < 4 ? 0x0B090200u : 0x0C0A0301u) : (wv < 12 ? 0x13111008u : 0x1412241Cu);
    const int rl = (rtab >> (8 * (warp & 3))) & 0xff, type = rl >> 3, c = rl & 7;
    const int H = (type == 1 || type == 2) ? 1 : 0, T0 = 8 * H;
    uint32_t toff = CV_SM_T + c * TAPB + (TPAD + e) * 8;
    uint32_t ubase = smem_u32(Us + c * ULEN);
    const uint32_t bbase = smem_u32(sm + CV_SM_B + c * BX_LEN);
    uint32_t rd0, rd1;
    {
        const uint32_t rstart = wv < 8 ? (wv < 4 ? 0x02000000u : 0x06040000u) : (wv < 12 ? 0x0C0B0A08u : 0x1E1D150Fu);
        const uint32_t rcount = wv < 8 ? 0x02020000u : (wv < 12 ? 0x03010102u : 0x01010806u);
        rd0 = (rstart >> (8 * (warp & 3))) & 0xff; rd1 = rd0 + ((rcount >> (8 * (warp & 3))) & 0xff);
    }
    asm volatile("" : "+r"(lds_off[0]), "+r"(lds_off[1]), "+r"(lds_off[2]), "+r"(lds_off[3]), "+r"(ubase), "+r"(toff), "+r"(rd0), "+r"(rd1));
    const uint2* Tc = reinterpret_cast<const uint2*>(sm + toff);
    TSTAMP1X(9, 256);
    unsigned short dskr;
    asm volatile("ld.global.nc.u16 %0, [%1];" : "=h"(dskr) : "l"(Dskip + d0 + min(lane, CV_CPB - 1)));
    if (tid >= 256) {
        const int t2 = tid - 256;
        if (t2 == 0) {
            mbar_init(smem_u32(sm + CV_SM_CNT) + 104, 1);
            asm volatile("fence.mbarrier_init.release.cluster;" ::: "memory");
            mbar_expect_tx(smem_u32(sm + CV_SM_CNT) + 104, CV_CPB * 2048);
            bulk_load(smem_u32(sm + CV_SM_O), tap + d0 * 128, CV_CPB * 2048, smem_u32(sm + CV_SM_CNT) + 104);
        } else if (lane == 0) {
            mbar_init(smem_u32(sm + CV_SM_CNT) + 16 * (warp - 9), warp == 15 ? 16 : 1);
            if (warp < 15) mbar_init(smem_u32(sm + CV_SM_CNT) + 16 * (warp - 9) + 8, 1);
            else if (layer) prefetch_tmap(&tmOut);
        }
        if (t2 < 149) {
            const int k = t2;
            const int off = k < 18 ? BX_5 + 8 * k : k < 37 ? BX_3 + 8 * (k - 18) : k < 69 ? BX_9 + 8 * (k - 37) : k < 101 ? BX_7 + 8 * (k - 69)
                          : k < 133 ? 8 * (k - 101) : (UPADF + SEQ) * 2 + 8 * (k - 133);
#pragma unroll
            for (int c = 0; c < CV_CPB; c++) *reinterpret_cast<uint2*>(sm + (k < 101 ? CV_SM_B + c * BX_LEN : CV_SM_U + c * ULEN * 2) + off) = make_uint2(0, 0);
        }
        asm volatile("bar.sync 1, 256;" ::: "memory");
        TSTAMP1X(10, 256);
        mbar_wait(smem_u32(sm + CV_SM_CNT) + 104, 0);
        TSTAMP1X(11, 256);
        {
            const int rx = (t2 & 15) < 4 ? t2 & 15 : 256 + (t2 & 15), cx = min(t2 >> 4, 4);
            uint32_t w[CV_CPB + 1][4];
#pragma unroll
            for (int c = 0; c <= CV_CPB; c++) {
                const uint32_t* E2 = reinterpret_cast<const uint32_t*>(sm + CV_SM_O) + (c < CV_CPB ? 512 * c + t2 + 7 : 512 * cx + rx + 3);
                w[c][0] = E2[0]; w[c][1] = E2[1]; w[c][2] = E2[4]; w[c][3] = E2[5];
            }
#pragma unroll
            for (int c = 0; c <= CV_CPB; c++)
                *reinterpret_cast<uint4*>(sm + CV_SM_T + (c < CV_CPB ? c * TAPB + (t2 + 4) * 16 : cx * TAPB + rx * 16)) =
                    make_uint4(__byte_perm(w[c][1], w[c][0], 0x7610), __byte_perm(w[c][3], w[c][2], 0x7610), __byte_perm(w[c][1], 0, 0x1032), __byte_perm(w[c][3], 0, 0x1032));
        }
        asm volatile("bar.arrive 2, 512;" ::: "memory");
        if ((t2 & 127) < 120) {
            const int r = 272 + (t2 & 127), c0 = t2 >> 7;
            const bool cc = r >= 368;
            const uint32_t* E2 = reinterpret_cast<const uint32_t*>(sm + CV_SM_O) + 512 * c0 + (r < 320 ? 301 + 2 * (r - 272) : cc ? 417 : 401 + 2 * (r - 320));
            const uint32_t* E3 = E2 + (cc ? 0 : 1);
            const uint32_t s0 = !cc ? 0x7610u : r == 382 ? 0x1044u : 0x4444u, s1 = !cc ? 0x7610u : r == 378 ? 0x1044u : 0x4444u;
            const uint32_t s2 = !cc ? 0x1032u : r == 381 ? 0x4410u : 0x4444u, s3 = !cc ? 0x1032u : r == 377 ? 0x4410u : 0x4444u;
            uint32_t w[3][4];
#pragma unroll
            for (int c = 0; c < 3; c++) { const int o = c < 2 ? 1024 * c : 2048 - 512 * c0; w[c][0] = E2[o]; w[c][1] = E2[o + 1]; w[c][2] = E3[o]; w[c][3] = E3[o + 1]; }
#pragma unroll
            for (int c = 0; c < 3; c++) {
                const uint32_t a = __byte_perm(w[c][3], w[c][2], s1), b = __byte_perm(w[c][1], w[c][0], s2);
                *reinterpret_cast<uint4*>(sm + CV_SM_T + (c < 2 ? 2 * c + c0 : 4) * TAPB + r * 16) =
                    make_uint4(__byte_perm(w[c][1], w[c][0], s0), cc ? a : b, cc ? b : a, __byte_perm(w[c][3], w[c][2], s3));
            }
        }
        TSTAMP1X(12, 256);
        if (layer == 0) {
#pragma unroll
            for (int c = 0; c < CV_CPB; c++) reinterpret_cast<uint4*>(yT + (size_t)(d0 + c) * XCP)[t2] = make_uint4(~0u, ~0u, ~0u, ~0u);
        }
        pdl_sync();
        if (layer && blockIdx.x == 0 && t2 == 0) g_epoch = ld_epoch();
        __syncwarp();
        asm volatile("bar.sync 3, 512;" ::: "memory");
    } else {
        const uint4* ppv = piv + tid;
        const float4* psv = sum + tid;
        const uint2* pxv = reinterpret_cast<const uint2*>(x1T + (size_t)d0 * XCP) + (tid >> 4) * 32 + (tid & 15);
        asm volatile("st.shared.u64 [%0], %1;" ::"r"(smem_u32(Ys) + tid * 8), "l"((uint64_t)ppv ^ (uint64_t)psv ^ (uint64_t)pxv) : "memory");
        pdl_sync();
        SPAN(3 + 4 * layer, 1);
        TSTAMP(0);
        if (threadIdx.x == 0) { GSTAMP(g_tim, 15); }
        float4 sv[4];
#pragma unroll
        for (int k = 0; k < 4; k++) sv[k] = CV_LD(psv + 256 * k);
        const uint4 pv = CV_LD(ppv);
        uint2 xe[CV_CPB], xo[CV_CPB];
#pragma unroll
        for (int c = 0; c < CV_CPB; c++) { xe[c] = CV_LDX(pxv + c * (XCP / 4)); xo[c] = CV_LDX(pxv + c * (XCP / 4) + 16); }
        uint32_t mw[4];
        float rs[8];
#pragma unroll
        for (int k = 0; k < 4; k++) {
            const uint32_t pw = k == 0 ? pv.x : k == 1 ? pv.y : k == 2 ? pv.z : pv.w;
            const float d0_ = sv[k].x * (1.0f / DM), d1_ = sv[k].z * (1.0f / DM);
            mw[k] = pack2(__uint_as_float(pw << 16) + d0_, __uint_as_float(pw & 0xffff0000u) + d1_);
            const uint32_t vr = pack2(fmaxf(fmaf(-d0_, d0_, sv[k].y * (1.0f / DM)), 0.f), fmaxf(fmaf(-d1_, d1_, sv[k].w * (1.0f / DM)), 0.f));
            const uint32_t ve = pack2(__uint_as_float(vr << 16) + 1e-5f, __uint_as_float(vr & 0xffff0000u) + 1e-5f);
            const uint32_t sd = pack2(sqrt_apx(__uint_as_float(ve << 16)), sqrt_apx(__uint_as_float(ve & 0xffff0000u)));
            rs[2 * k] = rcp_apx(__uint_as_float(sd << 16)); rs[2 * k + 1] = rcp_apx(__uint_as_float(sd & 0xffff0000u));
        }
        if (rs[0] != 123.f) TSTAMP(13);
        const int ch = tid + UPADF / 8, pch = ch ^ ((ch >> 3) & 1);
#pragma unroll
        for (int c = 0; c < CV_CPB; c++) {
            *reinterpret_cast<uint4*>(Xs + c * XLEN + tid * 8) = make_uint4(xe[c].x, xe[c].y, xo[c].x, xo[c].y);
            const uint32_t e0 = sub2(xe[c].x, mw[0]), e1 = sub2(xe[c].y, mw[1]), o0 = sub2(xo[c].x, mw[2]), o1 = sub2(xo[c].y, mw[3]);
            *reinterpret_cast<uint4*>(Us + c * ULEN + pch * 8) =
                make_uint4(pack2(__uint_as_float(e0 << 16) * rs[0], __uint_as_float(o0 << 16) * rs[4]), pack2(__uint_as_float(e0 & 0xffff0000u) * rs[1], __uint_as_float(o0 & 0xffff0000u) * rs[5]),
                           pack2(__uint_as_float(e1 << 16) * rs[2], __uint_as_float(o1 << 16) * rs[6]), pack2(__uint_as_float(e1 & 0xffff0000u) * rs[3], __uint_as_float(o1 & 0xffff0000u) * rs[7]));
        }
        asm volatile("bar.arrive 3, 512;" ::: "memory");
        asm volatile("bar.sync 2, 512;" ::: "memory");
    }
    TSTAMP(1);
#pragma unroll 1
    for (int rd = rd0; rd < (int)rd1; rd++) {
        const int i = 32 * rd + lane;
        if (i < CV_CPB * 193) {
            const int c = i / 193, chunk = i - c * 193 - 1, ch = chunk + UPADF / 8;
            const bf16* uc = Us + c * ULEN;
            const uint4 o = *reinterpret_cast<const uint4*>(uc + (ch ^ ((ch >> 3) & 1)) * 8);
            const uint2 lo = *reinterpret_cast<const uint2*>(uc + ((ch - 1) ^ (((ch - 1) >> 3) & 1)) * 8 + 4);
            const uint2 hi = *reinterpret_cast<const uint2*>(uc + ((ch + 1) ^ (((ch + 1) >> 3) & 1)) * 8);
            const uint32_t w[8] = {lo.x, lo.y, o.x, o.y, o.z, o.w, hi.x, hi.y};
            float v[16], b[8];
#pragma unroll
            for (int k = 0; k < 8; k++) { v[2 * k] = __uint_as_float(w[k] << 16); v[2 * k + 1] = __uint_as_float(w[k] & 0xffff0000u); }
            unsigned char* bx = sm + CV_SM_B + c * BX_LEN + chunk * 16;
#pragma unroll
            for (int k = 0; k < 8; k++) b[k] = v[k + 4] + (v[k + 3] + v[k + 5]);
            *reinterpret_cast<uint2*>(bx + BX_3 + 168) = make_uint2(pack2(b[0], b[1]), pack2(b[2], b[3]));
            *reinterpret_cast<uint2*>(bx + BX_3 + 176) = make_uint2(pack2(b[4], b[5]), pack2(b[6], b[7]));
#pragma unroll
            for (int k = 0; k < 8; k++) b[k] += v[k + 2] + v[k + 6];
            *reinterpret_cast<uint4*>(bx + BX_5 + 160) = make_uint4(pack2(b[0], b[1]), pack2(b[2], b[3]), pack2(b[4], b[5]), pack2(b[6], b[7]));
            if (chunk < 128) {
#pragma unroll
                for (int k = 0; k < 8; k++) b[k] += v[k + 1] + v[k + 7];
                *reinterpret_cast<uint4*>(bx + BX_7 + 272) = make_uint4(pack2(b[0], b[1]), pack2(b[2], b[3]), pack2(b[4], b[5]), pack2(b[6], b[7]));
#pragma unroll
                for (int k = 0; k < 8; k++) b[k] += v[k] + v[k + 8];
                *reinterpret_cast<uint4*>(bx + BX_9 + 272) = make_uint4(pack2(b[0], b[1]), pack2(b[2], b[3]), pack2(b[4], b[5]), pack2(b[6], b[7]));
            }
        }
    }
    __syncwarp();
    if (lane == 0) mbar_arrive(smem_u32(sm + CV_SM_CNT) + 96);
    TSTAMP(2);
    {
        float acc[8][4];
#pragma unroll
        for (int j = 0; j < 8; j++)
#pragma unroll
            for (int k = 0; k < 4; k++) acc[j][k] = 0.f;
#pragma unroll 1
        for (int pass = (type == 2 || type == 4) ? 1 : 0; pass < ((type == 1 || type == 3) ? 1 : 2); pass++) {
            const uint32_t o0 = pass ? lds_off[2] : lds_off[0], o1 = pass ? lds_off[3] : lds_off[1];
            if (H) direct_pass<true>(acc, ubase + T0 * 256, o0, o1, Tc + 64 * pass, pass == 0);
            else direct_pass<false>(acc, ubase, o0, o1, Tc + 64 * pass, pass == 0);
        }
        TSTAMP(6);
        mbar_wait(smem_u32(sm + CV_SM_CNT) + 96, 0);
        if (type != 1 && type != 4) {
            const uint32_t* w2 = reinterpret_cast<const uint32_t*>(sm + CV_SM_T + c * TAPB + TAP_W2) + (115 - 96) + 4 * g - 2 * ti;
            uint32_t f[10][2];
#pragma unroll
            for (int k = 0; k < 10; k++) { f[k][0] = w2[16 * k]; f[k][1] = w2[16 * k - 8]; }
            const uint32_t ab = bbase + off2 + (2 * T0 + 6) * 128;
            const int kmax = H ? 23 : 8;
            uint32_t a[3][4];
            ldsm_x4_t(a[0], ab);
            ldsm_x4_t(a[1], ab - 128);
#pragma unroll
            for (int kp = 0; kp < 24; kp++) {
                if (kp > kmax) break;
                if (kp < 22) ldsm_x4_t(a[(kp + 2) % 3], ab - min(kp + 2, kmax) * 128);
#pragma unroll
                for (int j = 0; j < 8; j++) {
                    const int ee = 2 * j - 14 + kp;
                    if (ee >= 0 && ee <= 9) mma_bf16(acc[j], a[kp % 3][0], a[kp % 3][1], a[kp % 3][2], a[kp % 3][3], f[ee][0], f[ee][1]);
                }
            }
        }
        TSTAMP(7);
        if (type != 2 && type != 4) {
            const uint32_t* w3 = reinterpret_cast<const uint32_t*>(sm + CV_SM_T + c * TAPB + TAP_W3) + (129 - 96) + 2 * (g - ti);
            uint32_t f[9][2];
#pragma unroll
            for (int k = 0; k < 9; k++) { f[k][0] = w3[16 * k]; f[k][1] = w3[16 * k - 8]; }
            const uint32_t ab = bbase + off3 + (T0 - 2) * 256;
            uint32_t a[3][4];
            ldsm_x4_t(a[0], ab);
            ldsm_x4_t(a[1], ab - H * 256);
#pragma unroll
            for (int kp = 0; kp < 9; kp++) {
                if (kp > T0) break;
                if (kp < 7) ldsm_x4_t(a[(kp + 2) % 3], ab - min(kp + 2, T0) * 256);
#pragma unroll
                for (int j = 0; j < 8; j++) {
                    const int dl = j - 7 + kp;
                    if (dl >= 0 && dl <= 8) mma_bf16(acc[j], a[kp % 3][0], a[kp % 3][1], a[kp % 3][2], a[kp % 3][3], f[dl][0], f[dl][1]);
                }
            }
            const uint2* Dc = reinterpret_cast<const uint2*>(sm + CV_SM_T + c * TAPB + TAP_C) + e;
            const uint2 h63 = Dc[16], h64 = Dc[32], l63 = Dc[8], l64 = Dc[24];
#pragma unroll
            for (int j = 0; j < 8; j++)
                if (j == 7 || H) {
                    uint32_t bq[4];
                    ldsm_x4(bq, ubase + offc + (T0 + j - 8) * 256);
                    mma_bf16(acc[j], h64.x, h64.y, l64.x, l64.y, bq[0], bq[1]);
                    mma_bf16(acc[j], h63.x, h63.y, l63.x, l63.y, bq[2], bq[3]);
                }
        }
        TSTAMP(8);
        int hh = (0x14 >> type) & 1;
        asm volatile("" : "+r"(hh));
        const bool hi_half = hh;
        if (type != 0) {
            const int pair = H ? c : 5;
            float4* give = reinterpret_cast<float4*>(sm + CV_SM_P + pair * 4096 + (hi_half ? 2048 : 0)) + lane;
            const float4* take = reinterpret_cast<const float4*>(sm + CV_SM_P + pair * 4096 + (hi_half ? 0 : 2048)) + lane;
            const uint32_t pb = smem_u32(sm + CV_SM_CNT) + pair * 16;
#pragma unroll
            for (int j = 0; j < 8; j++)
                asm volatile("{\n.reg .pred p;\nsetp.eq.s32 p, %5, %6;\n@p st.shared.v4.f32 [%0], {%1,%2,%3,%4};\n}"
                             ::"r"(smem_u32(give + 32 * (j & 3))), "f"(acc[j][0]), "f"(acc[j][1]), "f"(acc[j][2]), "f"(acc[j][3]), "r"(hh), "r"(j < 4 ? 1 : 0) : "memory");
            __syncwarp();
            if (lane == 0) mbar_arrive(pb + (hi_half ? 8 : 0));
            mbar_wait(pb + (hi_half ? 0 : 8), 0);
#pragma unroll
            for (int j = 0; j < 4; j++) {
                const float4 v = take[32 * j];
                acc[j][0] = (hi_half ? acc[j + 4][0] : acc[j][0]) + v.x; acc[j][1] = (hi_half ? acc[j + 4][1] : acc[j][1]) + v.y;
                acc[j][2] = (hi_half ? acc[j + 4][2] : acc[j][2]) + v.z; acc[j][3] = (hi_half ? acc[j + 4][3] : acc[j][3]) + v.w;
            }
        }
        const uint32_t dk = __shfl_sync(~0u, (uint32_t)dskr, c) * 0x10001u;
#pragma unroll 1
        for (int rnd = 0; rnd < (type == 0 ? 2 : 1); rnd++) {
            const int Q = 2 * H + (hi_half ? 1 : rnd);
            if (rnd) {
#pragma unroll
                for (int j = 0; j < 4; j++)
#pragma unroll
                    for (int k = 0; k < 4; k++) acc[j][k] = acc[j + 4][k];
            }
            const uint32_t ya = smem_u32(Ys + c * XLEN) + (128 * (4 * Q + (lane >> 4)) + 16 * (lane & 7) + 8 * ((lane >> 3) & 1)) * 2;
#pragma unroll
            for (int j = 0; j < 4; j += 2)
                asm volatile("stmatrix.sync.aligned.m8n8.x4.trans.shared.b16 [%0], {%1,%2,%3,%4};" ::"r"(ya + j * 256),
                             "r"(pack2(acc[j][0], acc[j][1])), "r"(pack2(acc[j][2], acc[j][3])),
                             "r"(pack2(acc[j + 1][0], acc[j + 1][1])), "r"(pack2(acc[j + 1][2], acc[j + 1][3])) : "memory");
            __syncwarp();
            uint4 yv[2], xv[2], uv[2];
#pragma unroll
            for (int k = 0; k < 2; k++) {
                const int t = 512 * Q + 256 * k + 8 * lane, cu = (t + UPADF) >> 3;
                yv[k] = *reinterpret_cast<const uint4*>(Ys + c * XLEN + t);
                xv[k] = *reinterpret_cast<const uint4*>(Xs + c * XLEN + t);
                uv[k] = *reinterpret_cast<const uint4*>(Us + c * ULEN + (cu ^ ((cu >> 3) & 1)) * 8);
            }
#pragma unroll
            for (int k = 0; k < 2; k++) {
                const uint32_t z0 = fin2(yv[k].x, uv[k].x, dk), z1 = fin2(yv[k].y, uv[k].y, dk), z2 = fin2(yv[k].z, uv[k].z, dk), z3 = fin2(yv[k].w, uv[k].w, dk);
                if (layer)
                    asm volatile("st.relaxed.gpu.global.v4.u32 [%0], {%1,%2,%3,%4};" ::"l"(dst + (size_t)(d0 + c) * XCP + 512 * Q + 256 * k + 8 * lane),
                                 "r"(add2(__byte_perm(xv[k].x, xv[k].z, 0x5410), z0)), "r"(add2(__byte_perm(xv[k].x, xv[k].z, 0x7632), z1)),
                                 "r"(add2(__byte_perm(xv[k].y, xv[k].w, 0x5410), z2)), "r"(add2(__byte_perm(xv[k].y, xv[k].w, 0x7632), z3)) : "memory");
                else {
                    uint2* dp = reinterpret_cast<uint2*>(dst + (size_t)(d0 + c) * XCP + 512 * Q + 256 * k) + (lane >> 4) * 32 + (lane & 15);
                    dp[0] = make_uint2(add2(xv[k].x, __byte_perm(z0, z1, 0x5410)), add2(xv[k].y, __byte_perm(z2, z3, 0x5410)));
                    dp[16] = make_uint2(add2(xv[k].z, __byte_perm(z0, z1, 0x7632)), add2(xv[k].w, __byte_perm(z2, z3, 0x7632)));
                }
            }
        }
        TSTAMP(4);
        if (layer == 1) {
            const int mb = blockIdx.x >> 3, cg = blockIdx.x & 7;
            const bf16* src = dst + (size_t)(cg * 80 + (tid >> 4)) * XCP + mb * 128 + (tid & 15) * 8;
            uint32_t v[3][4];
            __syncthreads();
            TSTAMP(5);
            uint32_t todo = warp < 8 ? 7 : 3;
#pragma unroll 1
            for (int it = 0; it < SPIN_MAX; it++) {
#pragma unroll
                for (int k = 0; k < 3; k++)
                    if (todo >> k & 1)
                        asm volatile("ld.relaxed.gpu.global.v4.u32 {%0,%1,%2,%3}, [%4];" : "=r"(v[k][0]), "=r"(v[k][1]), "=r"(v[k][2]), "=r"(v[k][3]) : "l"(src + k * (32 * XCP)) : "memory");
#pragma unroll
                for (int k = 0; k < 3; k++)
                    if ((todo >> k & 1) && v[k][0] != ~0u && v[k][1] != ~0u && v[k][2] != ~0u && v[k][3] != ~0u) {
                        *reinterpret_cast<uint4*>(sm + (32 * k + (tid >> 4)) * 272 + (tid & 15) * 16) = make_uint4(v[k][0], v[k][1], v[k][2], v[k][3]);
                        todo ^= 1u << k;
                    }
                if (!todo) break;
                __nanosleep(CV_SLEEP);
            }
            __syncthreads();
            uint32_t w[12];
#pragma unroll
            for (int k = 0; k < 3; k++) ldsm_x4(&w[4 * k], smem_u32(sm) + min(32 * k + lane, 79) * 272 + warp * 16);
            const uint32_t ot = smem_u32(sm + CV_SM_O) + warp * 1280, oa = ot + (lane & 7) * 160 + (lane >> 3) * 16;
            stsm_x4_t(oa, w[0], w[1], w[2], w[3]);
            stsm_x4_t(oa + 64, w[4], w[5], w[6], w[7]);
            asm volatile("stmatrix.sync.aligned.m8n8.x2.trans.shared.b16 [%0], {%1,%2};" ::"r"(oa + 128), "r"(w[8]), "r"(w[9]) : "memory");
            fence_async_smem();
            __syncwarp();
            if (lane == 0) tma_store_2d(&tmOut, cg * 80, mb * 128 + 8 * warp, ot);
        }
    }
    TSTAMP(3);
    GSTAMP(g_tim, 14);
    SPAN(3 + 4 * layer, 3);
}

__device__ __forceinline__ void wgmma_fence() { asm volatile("wgmma.fence.sync.aligned;" ::: "memory"); }
__device__ __forceinline__ void wgmma_commit() { asm volatile("wgmma.commit_group.sync.aligned;" ::: "memory"); }
template <int N> __device__ __forceinline__ void wgmma_wait() { asm volatile("wgmma.wait_group.sync.aligned %0;" ::"n"(N) : "memory"); }
__device__ __forceinline__ uint64_t make_desc(uint32_t addr, uint32_t lbo, uint32_t sbo, uint32_t mode) {
    return (uint64_t)((addr & 0x3FFFF) >> 4) | ((uint64_t)(lbo >> 4) << 16) | ((uint64_t)(sbo >> 4) << 32) | ((uint64_t)mode << 62);
}
template <int TA, int TB>
__device__ __forceinline__ void wgmma_n240(float (&d)[120], uint64_t da, uint64_t db, int acc) {
    asm volatile("{\n.reg .pred p;\nsetp.ne.b32 p, %124, 0;\nwgmma.mma_async.sync.aligned.m64n240k16.f32.bf16.bf16 {%0,%1,%2,%3,%4,%5,%6,%7,%8,%9,%10,%11,%12,%13,%14,%15,%16,%17,%18,%19,%20,%21,%22,%23,%24,%25,%26,%27,%28,%29,%30,%31,%32,%33,%34,%35,%36,%37,%38,%39,%40,%41,%42,%43,%44,%45,%46,%47,%48,%49,%50,%51,%52,%53,%54,%55,%56,%57,%58,%59,%60,%61,%62,%63,%64,%65,%66,%67,%68,%69,%70,%71,%72,%73,%74,%75,%76,%77,%78,%79,%80,%81,%82,%83,%84,%85,%86,%87,%88,%89,%90,%91,%92,%93,%94,%95,%96,%97,%98,%99,%100,%101,%102,%103,%104,%105,%106,%107,%108,%109,%110,%111,%112,%113,%114,%115,%116,%117,%118,%119}, %120, %121, p, 1, 1, %122, %123;\n}"
                 : "+f"(d[0]), "+f"(d[1]), "+f"(d[2]), "+f"(d[3]), "+f"(d[4]), "+f"(d[5]), "+f"(d[6]), "+f"(d[7]), "+f"(d[8]), "+f"(d[9]), "+f"(d[10]), "+f"(d[11]), "+f"(d[12]), "+f"(d[13]), "+f"(d[14]), "+f"(d[15]), "+f"(d[16]), "+f"(d[17]), "+f"(d[18]), "+f"(d[19]), "+f"(d[20]), "+f"(d[21]), "+f"(d[22]), "+f"(d[23]), "+f"(d[24]), "+f"(d[25]), "+f"(d[26]), "+f"(d[27]), "+f"(d[28]), "+f"(d[29]), "+f"(d[30]), "+f"(d[31]), "+f"(d[32]), "+f"(d[33]), "+f"(d[34]), "+f"(d[35]), "+f"(d[36]), "+f"(d[37]), "+f"(d[38]), "+f"(d[39]), "+f"(d[40]), "+f"(d[41]), "+f"(d[42]), "+f"(d[43]), "+f"(d[44]), "+f"(d[45]), "+f"(d[46]), "+f"(d[47]), "+f"(d[48]), "+f"(d[49]), "+f"(d[50]), "+f"(d[51]), "+f"(d[52]), "+f"(d[53]), "+f"(d[54]), "+f"(d[55]), "+f"(d[56]), "+f"(d[57]), "+f"(d[58]), "+f"(d[59]), "+f"(d[60]), "+f"(d[61]), "+f"(d[62]), "+f"(d[63]), "+f"(d[64]), "+f"(d[65]), "+f"(d[66]), "+f"(d[67]), "+f"(d[68]), "+f"(d[69]), "+f"(d[70]), "+f"(d[71]), "+f"(d[72]), "+f"(d[73]), "+f"(d[74]), "+f"(d[75]), "+f"(d[76]), "+f"(d[77]), "+f"(d[78]), "+f"(d[79]), "+f"(d[80]), "+f"(d[81]), "+f"(d[82]), "+f"(d[83]), "+f"(d[84]), "+f"(d[85]), "+f"(d[86]), "+f"(d[87]), "+f"(d[88]), "+f"(d[89]), "+f"(d[90]), "+f"(d[91]), "+f"(d[92]), "+f"(d[93]), "+f"(d[94]), "+f"(d[95]), "+f"(d[96]), "+f"(d[97]), "+f"(d[98]), "+f"(d[99]), "+f"(d[100]), "+f"(d[101]), "+f"(d[102]), "+f"(d[103]), "+f"(d[104]), "+f"(d[105]), "+f"(d[106]), "+f"(d[107]), "+f"(d[108]), "+f"(d[109]), "+f"(d[110]), "+f"(d[111]), "+f"(d[112]), "+f"(d[113]), "+f"(d[114]), "+f"(d[115]), "+f"(d[116]), "+f"(d[117]), "+f"(d[118]), "+f"(d[119])
                 : "l"(da), "l"(db), "n"(TA), "n"(TB), "r"(acc));
}

__device__ __forceinline__ void wgmma_n80(float (&d)[40], uint64_t da, uint64_t db, int acc) {
    asm volatile("{\n.reg .pred p;\nsetp.ne.b32 p, %42, 0;\nwgmma.mma_async.sync.aligned.m64n80k16.f32.bf16.bf16 {%0,%1,%2,%3,%4,%5,%6,%7,%8,%9,%10,%11,%12,%13,%14,%15,%16,%17,%18,%19,%20,%21,%22,%23,%24,%25,%26,%27,%28,%29,%30,%31,%32,%33,%34,%35,%36,%37,%38,%39}, %40, %41, p, 1, 1, 0, 1;\n}"
                 : "+f"(d[0]), "+f"(d[1]), "+f"(d[2]), "+f"(d[3]), "+f"(d[4]), "+f"(d[5]), "+f"(d[6]), "+f"(d[7]), "+f"(d[8]), "+f"(d[9]), "+f"(d[10]), "+f"(d[11]), "+f"(d[12]), "+f"(d[13]), "+f"(d[14]), "+f"(d[15]), "+f"(d[16]), "+f"(d[17]), "+f"(d[18]), "+f"(d[19]), "+f"(d[20]), "+f"(d[21]), "+f"(d[22]), "+f"(d[23]), "+f"(d[24]), "+f"(d[25]), "+f"(d[26]), "+f"(d[27]), "+f"(d[28]), "+f"(d[29]), "+f"(d[30]), "+f"(d[31]), "+f"(d[32]), "+f"(d[33]), "+f"(d[34]), "+f"(d[35]), "+f"(d[36]), "+f"(d[37]), "+f"(d[38]), "+f"(d[39])
                 : "l"(da), "l"(db), "r"(acc));
}

constexpr int A1_THREADS = 384;
constexpr int A1_NST = 4;
#define A1_SKEW 8
constexpr int A1_STAGE = 16384 + WQ_STAGE;
constexpr int A1_KVP = 336;
constexpr int A1_SM_KV = 2 * A1_STAGE;
constexpr int A1_SM_BAR = A1_NST * A1_STAGE;
constexpr int A1_SM_RS = A1_SM_BAR + 512;
constexpr int A1_SM_W0 = A1_SM_BAR + 3072, A1_SM_W3 = A1_SM_BAR - 3 * WOB, A1_SM_A1 = 2 * WOB, A1_SM_A0 = A1_SM_A1 + 61440;
constexpr int A1_SM_XA = A1_SM_W0 + 2 * WOB, A1_SM_XB = A1_SM_XA + 2048;
constexpr int A1_SMEM = A1_SM_W0 + 3 * WOB;
static_assert(A1_SM_W3 >= A1_SM_KV + 144 * A1_KVP && A1_SM_W3 % 512 == 0 && A1_SM_A1 % 1024 == 0 && A1_SM_A0 <= A1_SM_KV && A1_SM_A0 + 61440 <= A1_SM_W3 && A1_SMEM <= 232448, "layout");
__device__ __forceinline__ constexpr uint32_t wo_off(int h) { return h * WOB + (h < 3 ? A1_SM_W0 : h < 6 ? A1_SM_W3 - 3 * WOB : -6 * WOB); }
#define A1_FRED "red.relaxed.gpu.global.add.u32"
#define A1_FLD "ld.acquire.gpu.global.u32"
#define ST_SLEEP 20
#define ST_SLEEP0 300
#define WO_LATE bar_done
#define A1_P0 2
#define A1_PW (kb - 2)
#define A1_FSPIN SPIN_MAX
#define A1_FSLEEP 40
#define A1_WOAT 6

template <int L>
__device__ __forceinline__ void a1_mainloop(float (&acc)[120], uint32_t sbase, uint32_t bars, int wg, int tile) {
    constexpr int layer = L; (void)layer;
    const uint64_t da0 = L ? make_desc(sbase + wg * 8192, 8192, 1024, 1) : make_desc(sbase + wg * 8192, 16, 1024, 1), db0 = make_desc(sbase + 16384, 1024, 256, 3);
#pragma unroll 1
    for (int t = 0;; t++) {
        const int st = t % A1_NST;
        mbar_wait(bars + 8 * st, (t / A1_NST) & 1);
        if (t == A1_SKEW && wg == 0) mbar_wait(bars + 160, 0);
        TSTAMP3(1 + t);
        wgmma_fence();
#pragma unroll
        for (int kk = 0; kk < 4; kk++) wgmma_n240<L, 1>(acc, da0 + (uint32_t)(st * (A1_STAGE / 16) + kk * (L ? 128 : 2)), db0 + (uint32_t)(st * (A1_STAGE / 16) + (kk >> 1) * (WQ_STAGE / 32) + (kk & 1) * 32), kk ? 1 : t);
        wgmma_commit();
        if (t == 9) break;
        if (t == A1_SKEW - 1 && wg == 0) wgmma_wait<0>(); else wgmma_wait<1>();
        if (t > 0 && (threadIdx.x & 127) == 0) {
            if (t != A1_SKEW || wg) mbar_arrive(bars + 8 * (A1_NST + (t - 1) % A1_NST));
            if (t == A1_SKEW - 1 && wg == 0) mbar_arrive(bars + 8 * (A1_NST + t % A1_NST));
        }
    }
}

__global__ void __launch_bounds__(A1_THREADS, 1) a1_kernel(const int layer, const bf16* __restrict__ x0, const unsigned char* __restrict__ wq, const unsigned char* __restrict__ wo,
                                                           float2* __restrict__ rsum, uint4* __restrict__ of, const __grid_constant__ CUtensorMap tmX,
                                                           const __grid_constant__ CUtensorMap tmR, const __grid_constant__ CUtensorMap tmX1, const __grid_constant__ TileTab tab) {
    extern __shared__ __align__(1024) unsigned char stg[];
    const uint32_t sbase = smem_u32(stg);
    const uint32_t bars = sbase + A1_SM_BAR;
    const uint32_t bar_stat = bars + 64, bar_kv = bars + 72, bar_rd = bars + 168;
    const uint32_t bar_wo = bars + 208, bar_done = bars + 216, bar_pv = bars + 224, bar_kvf = bars + 232, bar_f2 = bars + 248, bar_e2 = bars + 384, que = bars + 448;
    const int tid = threadIdx.x;
    const int w = __shfl_sync(~0u, tid >> 5, 0), wg = w >> 2;
    uint32_t smid, ns;
    asm volatile("mov.u32 %0, %smid;" : "=r"(smid));
    asm volatile("mov.u32 %0, %nsmid;" : "=r"(ns));
    const auto te = tab.e[ns == tab.ns ? smid : 132 + blockIdx.x];
    const int tile = te.tile, mb = te.mb, hg = te.hg;
    float2* rst = reinterpret_cast<float2*>(stg + A1_SM_RS) + 8;
    auto issue_w = [&](int it) { bulk_load(sbase + (it % A1_NST) * A1_STAGE + 16384, wq + te.woff + it * WQ_STAGE, WQ_STAGE, bars + 8 * (it % A1_NST)); };
    auto issue_x = [&](int it, int kb) {
        asm volatile("cp.async.bulk.tensor.5d.shared::cluster.global.mbarrier::complete_tx::bytes [%0], [%1, {%3, %3, %3, %4, %5}], [%2];"
                     ::"r"(sbase + (it % A1_NST) * A1_STAGE), "l"(&tmX), "r"(bars + 8 * (it % A1_NST)), "r"(0), "r"(mb), "r"(kb) : "memory");
    };
    if (w == 8 && tile < 128) {
        const bool one = elect();
        if (one) {
#pragma unroll
            for (int i = 0; i < A1_NST; i++) mbar_init(bars + 8 * i, 1);
            asm volatile("fence.mbarrier_init.release.cluster;" ::: "memory");
        }
        __syncwarp();
        asm volatile("bar.arrive 0, 384;" ::: "memory");
        if (one) {
#define PW asm volatile("griddepcontrol.wait;" ::: "memory");
            if (layer) { issue_w(0); PW issue_x(0, te.kb0); issue_x(1, te.kb0 + 1); }
            else { issue_x(0, te.kb0); issue_x(1, te.kb0 + 1); PW issue_w(0); }
            issue_w(1);
#pragma unroll
            for (int i = 0; i < A1_NST; i++) mbar_expect_tx(bars + 8 * i, A1_STAGE);
            asm volatile("griddepcontrol.launch_dependents;" ::: "memory");
#pragma unroll
            for (int kb = 2; kb < A1_P0; kb++) { issue_x(kb, te.kb0 + kb); issue_w(kb); }
            DBGC(34); DBGV(33, smid); DBGV(40, t_entry); DBGV(30, t_a); DBGV(31, t_b); DBGV(32, t_c); DBGV(38, t_d); DBGV(39, t_e);
        }
    }
    if (tile >= 128) { sm_idle(layer); return; }
    if (wg == 2) {
        if (w != 8) {
            if (tid == 320) { prefetch_tmap(&tmX); prefetch_tmap(&tmR); prefetch_tmap(&tmX1); }
            asm volatile("bar.sync 0, 384;" ::: "memory");
        }
        if (w == 9) {
            asm volatile("bar.arrive 3, 64;" ::: "memory");
            if (layer == 0) pdl_sync();
            float4 a[2] = {};
#pragma unroll
            for (int k = 0; k < 10; k++)
#pragma unroll
                for (int h = 0; h < 2; h++) {
                    const int c4 = min(tid - 288 + 32 * h, 59);
                    const float4 v = __ldcg(reinterpret_cast<const float4*>(g_csp + k * 1920 + hg * 80) + c4 + (c4 / 20) * 140);
                    a[h].x += v.x; a[h].y += v.y; a[h].z += v.z; a[h].w += v.w;
                }
#pragma unroll
            for (int h = 0; h < 2; h++)
#pragma unroll
                for (int k = 0; k < 4; k++) {
                    const float c = 0.5f * (k == 0 ? a[h].x : k == 1 ? a[h].y : k == 2 ? a[h].z : a[h].w), c1 = c - rbf(c), c2 = c1 - rbf(c1);
                    *reinterpret_cast<uint4*>(stg + A1_SM_XB + (4 * min(tid - 288 + 32 * h, 59) + k) * 16) = make_uint4(pack2(c, c1), pack2(c2, 0.f), 0u, 0u);
                }
            fence_async_smem();
            __syncwarp();
            if (tid == 288) mbar_arrive(bar_stat);
#pragma unroll 4
            for (int k = 0; k < 40; k++) asm volatile("st.global.v4.u32 [%0], {%1,%1,%1,%1};" ::"l"(of + (mb * 8 + hg) * 1280 + 32 * k + (tid - 288)), "r"(~0u) : "memory");
            asm volatile("fence.acq_rel.gpu;" ::: "memory");
            asm volatile("fence.proxy.async.global;" ::: "memory");
            __syncwarp();
            if (tid == 288) mbar_arrive(bar_done);
            TSTAMP1T(9, 288);
        } else if (w == 8) {
            asm volatile("bar.sync 3, 64;" ::: "memory");
            if (elect()) {
#pragma unroll 1
                for (int kb = A1_P0; kb < 10; kb++) {
                    if (kb < A1_NST) mbar_wait(bars + 8 * A1_PW, 0);
                    else {
                        mbar_wait(bars + 8 * (A1_NST + kb % A1_NST), ((kb / A1_NST) - 1) & 1);
                        if (layer && kb < 9) mbar_wait(bar_rd + 8 * (kb - A1_NST), 0);
                        mbar_expect_tx(bars + 8 * (kb % A1_NST), A1_STAGE);
                    }
                    issue_x(kb, kb < 5 ? kb + te.kb0 : kb - te.kb0); issue_w(kb);
                    if (kb == A1_WOAT) {
                        mbar_expect_tx(bar_wo, 8 * WOB);
                        bulk_load(sbase + A1_SM_W0, wo + hg * 8 * WOB, 2 * WOB, bar_wo);
                    }
                }
                TSTAMP1T(6, 256);
                mbar_wait(bars + 8 * (A1_NST + 3), 1);
                bulk_load(sbase + A1_SM_W3, wo + (hg * 8 + 3) * WOB, 3 * WOB, bar_wo);
            }
            __syncwarp();
        } else {
            const int j = tid - 320;
            const uint32_t tag = ld_epoch();
            if (tid == 352) sm_started(layer);
            if (layer == 0) {
                const uint4* src = reinterpret_cast<const uint4*>(x0 + (size_t)(mb * 128 + hg * 16 + (j >> 2)) * DM);
                uint4 v[20];
#pragma unroll
                for (int k = 0; k < 20; k++) v[k] = __ldg(src + (j & 3) + 4 * k);
                const float p0 = __uint_as_float(__shfl_sync(~0u, v[0].x, j & 28) << 16);
                float s[2] = {0.f, 0.f}, q[2] = {0.f, 0.f};
#pragma unroll
                for (int k = 0; k < 20; k++) {
                    const uint32_t w[4] = {v[k].x, v[k].y, v[k].z, v[k].w};
#pragma unroll
                    for (int i = 0; i < 4; i++) {
                        const float a = __uint_as_float(w[i] << 16) - p0, b = __uint_as_float(w[i] & 0xffff0000u) - p0;
                        s[0] += a; s[1] += b; q[0] = fmaf(a, a, q[0]); q[1] = fmaf(b, b, q[1]);
                    }
                }
                float s0 = s[0] + s[1], q0 = q[0] + q[1];
#pragma unroll
                for (int o = 1; o <= 2; o <<= 1) { s0 += __shfl_xor_sync(~0u, s0, o); q0 += __shfl_xor_sync(~0u, q0, o); }
                if ((j & 3) == 0) {
                    const float d = s0 * (1.0f / DM);
                    const uint32_t ms = pack2(p0 + d, sqrt_apx(rbf(rbf(fmaxf(fmaf(-d, d, q0 * (1.0f / DM)), 0.f)) + 1e-5f)));
                    asm volatile("st.global.cg.u64 [%0], %1;" ::"l"(g_rstat + mb * 128 + (j & 4) * 16 + hg * 8 + (j >> 3)), "l"(tagw(ms, tag)) : "memory");
                    g_piv[mb * 128 + hg * 16 + ((j >> 2) & 8) + (j & 4) + ((j >> 3) & 3)] = __ushort_as_bfloat16((unsigned short)ms);
                }
            }
            float o[4];
            int row;
            if (layer == 0) {
                ulonglong2 v;
#pragma unroll 1
                for (int it = 0; it < SPIN_MAX; it++) {
                    v = ld_tag2(reinterpret_cast<const ulonglong2*>(g_rstat + mb * 128) + j);
                    if (tag_ok(v, tag)) break;
                    __nanosleep(100);
                }
                o[0] = __uint_as_float((uint32_t)v.x << 16); o[1] = rcp_apx(__uint_as_float((uint32_t)v.x & 0xffff0000u));
                o[2] = __uint_as_float((uint32_t)v.y << 16); o[3] = rcp_apx(__uint_as_float((uint32_t)v.y & 0xffff0000u));
                row = 2 * j;
            } else {
                const int ch = j & 7, kg = (j >> 3) & 3;
                const unsigned char* src = stg + (j >> 5) * 8192 + (hg & 3) * 2048;
                float s[8], q[8], p0[8];
#pragma unroll
                for (int i = 0; i < 8; i++) { s[i] = 0.f; q[i] = 0.f; }
#pragma unroll 1
                for (int it = 0; it < 5; it++) {
                    uint4 v[4];
                    mbar_wait(bars + 8 * (it % A1_NST), it / A1_NST);
#pragma unroll
                    for (int k = 0; k < 4; k++) v[k] = *reinterpret_cast<const uint4*>(src + (it % A1_NST) * A1_STAGE + (4 * k + kg) * 128 + ((ch ^ ((4 * k + kg) & 7)) << 4));
                    if (it == 0) {
                        const uint4 pv = *reinterpret_cast<const uint4*>(src + (ch << 4));
                        const uint32_t w[4] = {pv.x, pv.y, pv.z, pv.w};
#pragma unroll
                        for (int i = 0; i < 4; i++) { p0[2 * i] = __uint_as_float(w[i] << 16); p0[2 * i + 1] = __uint_as_float(w[i] & 0xffff0000u); }
                    }
                    asm volatile("" :: "r"(v[0].x), "r"(v[1].x), "r"(v[2].x), "r"(v[3].x), "f"(p0[0]) : "memory");
                    __syncwarp();
                    if ((tid & 31) == 0) mbar_arrive(bar_rd + 8 * it);
#pragma unroll
                    for (int k = 0; k < 4; k++) {
                        const uint32_t w[4] = {v[k].x, v[k].y, v[k].z, v[k].w};
#pragma unroll
                        for (int i = 0; i < 4; i++) {
                            const float a = __uint_as_float(w[i] << 16) - p0[2 * i], b = __uint_as_float(w[i] & 0xffff0000u) - p0[2 * i + 1];
                            s[2 * i] += a; s[2 * i + 1] += b; q[2 * i] = fmaf(a, a, q[2 * i]); q[2 * i + 1] = fmaf(b, b, q[2 * i + 1]);
                        }
                    }
                }
#pragma unroll
                for (int i = 0; i < 4; i++) {
                    const bool up = kg & 2;
                    const float ss = __shfl_xor_sync(~0u, up ? s[i] : s[i + 4], 16), qq = __shfl_xor_sync(~0u, up ? q[i] : q[i + 4], 16);
                    s[i] = (up ? s[i + 4] : s[i]) + ss; q[i] = (up ? q[i + 4] : q[i]) + qq; p0[i] = up ? p0[i + 4] : p0[i];
                }
#pragma unroll
                for (int i = 0; i < 2; i++) {
                    const bool up = kg & 1;
                    const float ss = __shfl_xor_sync(~0u, up ? s[i] : s[i + 2], 8), qq = __shfl_xor_sync(~0u, up ? q[i] : q[i + 2], 8);
                    s[i] = (up ? s[i + 2] : s[i]) + ss; q[i] = (up ? q[i + 2] : q[i]) + qq; p0[i] = up ? p0[i + 2] : p0[i];
                }
                uint4* gp = g_halo + 86016 + mb * 512 + j;
                const float d0 = s[0] * (1.0f / 80.0f), d1 = s[1] * (1.0f / 80.0f);
                asm volatile("st.relaxed.gpu.global.v4.f32 [%0], {%1,%2,%3,%4};" ::"l"(gp + hg * 64), "f"(p0[0] + d0), "f"(fmaxf(fmaf(-d0, s[0], q[0]), 0.f)), "f"(p0[1] + d1), "f"(fmaxf(fmaf(-d1, s[1], q[1]), 0.f)) : "memory");
                __nanosleep(ST_SLEEP0);
                uint32_t pw[8][4], todo = 0xff;
#pragma unroll 1
                for (int it = 0; it < SPIN_MAX; it++) {
#pragma unroll
                    for (int k = 0; k < 8; k++)
                        if (todo >> k & 1) asm volatile("ld.relaxed.gpu.global.v4.u32 {%0,%1,%2,%3}, [%4];" : "=r"(pw[k][0]), "=r"(pw[k][1]), "=r"(pw[k][2]), "=r"(pw[k][3]) : "l"(gp + k * 64) : "memory");
#pragma unroll
                    for (int k = 0; k < 8; k++)
                        if (__all_sync(~0u, pw[k][0] != ~0u && pw[k][1] != ~0u && pw[k][2] != ~0u && pw[k][3] != ~0u)) todo &= ~(1u << k);
                    if (!todo) break;
                    __nanosleep(ST_SLEEP);
                }
#pragma unroll
                for (int r = 0; r < 2; r++) {
                    float mean = 0.f, m2 = 0.f;
#pragma unroll
                    for (int k = 0; k < 8; k++) mean += __uint_as_float(pw[k][2 * r]);
                    mean *= 0.125f;
#pragma unroll
                    for (int k = 0; k < 8; k++) {
                        const float dm = __uint_as_float(pw[k][2 * r]) - mean;
                        m2 += fmaf(80.0f * dm, dm, __uint_as_float(pw[k][2 * r + 1]));
                    }
                    o[2 * r] = rbf(mean);
                    o[2 * r + 1] = rcp_apx(rbf(sqrt_apx(rbf(rbf(m2 * (1.0f / DM)) + 1e-5f))));
                }
                row = (j >> 5) * 64 + (j & 7) * 8 + ((j >> 3) & 3) * 2;
                if (hg == 0) *reinterpret_cast<uint32_t*>(g_piv + SEQ + mb * 128 + 2 * (row & 60) + 4 * (row >> 6) + (row & 3)) = __byte_perm(__float_as_uint(o[0]), __float_as_uint(o[2]), 0x7632);
            }
#pragma unroll
            for (int r = 0; r < 2; r++)
                *reinterpret_cast<uint4*>(stg + A1_SM_XA + (row + r) * 16) = make_uint4(__byte_perm(__float_as_uint(-o[2 * r]), 0, 0x3232), __float_as_uint(-o[2 * r]) >> 16, 0u, 0u);
            *reinterpret_cast<float4*>(rst + row + (row >> 6) * 8) = make_float4(o[0], o[1], o[2], o[3]);
            fence_async_smem();
            TSTAMP1T(7, 320);
            if (tid == 320) DBGC(44);
            __syncwarp();
            if ((tid & 31) == 0) mbar_arrive(bar_stat);
        }
        if (tid == 320) DBGCAL(0);
        if (tid == 352) {
            mbar_wait(WO_LATE, 0);
            mbar_wait(bar_done, 0);
            bulk_load(sbase, wo + (hg * 8 + 6) * WOB, 2 * WOB, bar_wo);
            bulk_load(sbase + A1_SM_W0 + 2 * WOB, wo + (hg * 8 + 2) * WOB, WOB, bar_wo);
        }
        if (w < 10) {
            const int cw = w - 8;
            const uint32_t* fl = reinterpret_cast<const uint32_t*>(rsum + 2 * SEQ) + (((layer * 16 + mb) * 2 + cw) * 8 + (tid & 7)) * FSTR;
            const unsigned char* src = reinterpret_cast<const unsigned char*>(of) + mb * 163840 + cw * 10240 + (tid & 7) * 20480;
            const uint32_t sl = sbase + (cw ? A1_SM_A1 : A1_SM_A0);
            mbar_wait(cw ? bar_done : bar_kvf, 0);
            if ((tid & 31) == 0) {
                mbar_expect_tx(bar_f2 + 64 * cw + 64, 10240);
                tma_load_3d(sl + 51200, &tmR, layer ? 0 : hg * 80, layer ? hg * 80 : mb * 64, layer ? mb * 2 + cw : cw, bar_f2 + 64 * cw + 64);
            }
            __syncwarp();
            uint32_t pend = 0xffu & ~(1u << hg), v = 0;
            const uint32_t bo = wo_off((tid & 7) + ((tid & 7) < hg)) >> 4, lt = (1u << (tid & 31)) - 1;
#pragma unroll 1
            for (int it = 0; pend && it < 2 * SPIN_MAX; it++) {
                if (v != 4 && (pend >> (tid & 31) & 1)) asm volatile(A1_FLD " %0, [%1];" : "=r"(v) : "l"(fl) : "memory");
                uint32_t fr;
                asm volatile("{\n.reg .pred p;\nmbarrier.test_wait.parity.shared::cta.b64 p, [%1], 0;\nselp.b32 %0, 1, 0, p;\n}" : "=r"(fr) : "r"(bar_e2 + 16 * cw + (tid & 1) * 8) : "memory");
                fr = __ballot_sync(~0u, fr);
                uint32_t m = __ballot_sync(~0u, v == 4 || it >= A1_FSPIN) & pend;
                const int q = 8 - __popc(pend) + __popc(m & lt);
                m &= __ballot_sync(~0u, q < ((fr & 2) ? 8 : (fr & 1) ? 7 : 5));
                pend ^= m;
                if (m >> (tid & 31) & 1) DBGC(12 + cw * 8 + (tid & 7));
                if (!m) __nanosleep(A1_FSLEEP);
                else asm volatile("fence.proxy.async.global;" ::: "memory");
                if (m >> (tid & 31) & 1) {
                    bulk_load(q == 7 && !cw ? sbase + A1_SM_W0 : sl + (q < 6 ? q : q - 6) * 10240, src, 10240, bar_f2 + 64 * cw + 8 * q);
                    asm volatile("st.shared.u32 [%0], %1;" ::"r"(que + 32 * cw + 4 * q), "r"(bo) : "memory");
                    mbar_expect_tx(bar_f2 + 64 * cw + 8 * q, 10240);
                    DBGC(44 + cw * 8 + q);
                }
                __syncwarp();
            }
        }
    } else {
        if (tid == 0) {
            mbar_init(bar_stat, 3);
#pragma unroll
            for (int i = 0; i < 8; i++) mbar_init(bar_kv + 8 * i, 1);
            mbar_init(bars + 144, 1);
            mbar_init(bars + 160, 1);
#pragma unroll
            for (int i = 0; i < 5; i++) mbar_init(bar_rd + 8 * i, 2);
            asm volatile("fence.mbarrier_init.release.cluster;" ::: "memory");
        } else if (tid == 32) {
            mbar_init(bar_wo, 1); mbar_init(bar_done, 3); mbar_init(bar_pv, 4); mbar_init(bar_kvf, 8); mbar_init(bars + 240, 4);
#pragma unroll
            for (int i = 0; i < 4; i++) { mbar_init(bar_e2 + 8 * i, i == 1 ? 2 : 1); mbar_init(bars + 8 * (A1_NST + i), 2); }
            asm volatile("fence.mbarrier_init.release.cluster;" ::: "memory");
        } else if (tid == 64) {
#pragma unroll
            for (int i = 1; i <= 16; i++) mbar_init(bar_f2 + 8 * i, 1);
            asm volatile("fence.mbarrier_init.release.cluster;" ::: "memory");
        }
        asm volatile("bar.sync 0, 384;" ::: "memory");
        SPAN(1 + 4 * layer, 0);
        constexpr int on = 1;
        float acc[120];
        const int lane = tid & 31, warp = w & 7, g = lane >> 2, t = lane & 3;
        if (on) {
            SPAN(1 + 4 * layer, 1);
            TSTAMP1(0);
            if (threadIdx.x == 0) { GSTAMP(g_tim1, 15); }
            TSTAMP3(0);
            if (tid == 0) TSTAMP2(0);
            TSTAMP4(0);
            if (tid == 0) DBGC(60);
            if (layer == 0) a1_mainloop<0>(acc, sbase, bars, wg, tile); else a1_mainloop<1>(acc, sbase, bars, wg, tile);
            uint32_t ok;
            asm volatile("{\n.reg .pred p;\nmbarrier.test_wait.parity.shared::cta.b64 p, [%1], 0;\nselp.b32 %0, 1, 0, p;\n}" : "=r"(ok) : "r"(bar_stat) : "memory");
            if (tid == 128 && !ok) mbar_arrive(bars + 160);
            __syncwarp();
            mbar_wait(bar_stat, 0);
            wgmma_fence();
            wgmma_n240<0, 0>(acc, make_desc(sbase + A1_SM_XA + wg * 1024, 0, 128, 0), make_desc(sbase + A1_SM_XB, 0, 128, 0), 1);
            wgmma_commit();
            if (tid == 128 && ok) mbar_arrive(bars + 160);
            mbar_wait(bars + 8 * (A1_NST + 3), 1);
        }
        const float2* rw = rst + 16 * warp + 8 * wg;
        const float rb0 = rw[g + 8].y, ra = rw[g].y * 0.22360679774997896f, rb = rb0 * 0.22360679774997896f;
        wgmma_wait<0>();
        if ((tid & 127) == 0) mbar_arrive(bar_done);
        TSTAMP1(2);
        TSTAMP1T(13, 224);
        if ((tid & 127) == 0) DBGC(62 - wg);
        uint32_t f[2][30];
#pragma unroll
        for (int j = 10; j < 30; j++) f[1][j] = pack2(acc[4 * j + 2], acc[4 * j + 3]);
        if ((warp & 3) == 3) {
            uint4* hout = g_halo + (((layer * 16 + mb) * 8 + hg) * 2 + wg) * 168;
#pragma unroll
            for (int j = 0; j < 20; j += 4)
                asm volatile("st.relaxed.gpu.global.v4.u32 [%0], {%1,%2,%3,%4};" ::"l"(hout + 8 * j + lane), "r"(f[1][10 + j]), "r"(f[1][11 + j]), "r"(f[1][12 + j]), "r"(f[1][13 + j]) : "memory");
            if (t == 0) asm volatile("st.relaxed.gpu.global.f32 [%0], %1;" ::"l"(reinterpret_cast<float*>(hout + 160) + g), "f"(rb0) : "memory");
        }
        TSTAMP1T(12, 224);
        const uint32_t kvw = sbase + A1_SM_KV + (16 * warp + 8 * wg) * A1_KVP;
        const uint32_t mrow = kvw + (lane & 7) * A1_KVP + (lane >> 3) * 16;
#pragma unroll
        for (int j = 0; j < 20; j += 4) stsm_x4(mrow + 16 * A1_KVP + 16 * j, f[1][10 + j], f[1][11 + j], f[1][12 + j], f[1][13 + j]);
        __syncwarp();
        if (lane == 0 && (warp & 3) != 3) mbar_arrive(bar_kv + 8 * (warp + 1));
#pragma unroll
        for (int j = 0; j < 30; j++) f[0][j] = pack2(acc[4 * j], acc[4 * j + 1]);
        stsm_x4(mrow + 8 * A1_KVP + 160, f[0][20], f[0][21], f[0][22], f[0][23]);
        stsm_x4(mrow + 8 * A1_KVP + 224, f[0][24], f[0][25], f[0][26], f[0][27]);
        asm volatile("stmatrix.sync.aligned.m8n8.x2.shared.b16 [%0], {%1,%2};" ::"r"(mrow + 8 * A1_KVP + 288), "r"(f[0][28]), "r"(f[0][29]) : "memory");
#pragma unroll
        for (int j = 0; j < 10; j++) f[1][j] = pack2(acc[4 * j + 2], acc[4 * j + 3]);
        __syncwarp();
        uint32_t vb[10][2], vp[12], kp[12];
#pragma unroll
        for (int j = 0; j < 10; j += 2) ldsm_x4_t(&vb[j][0], kvw + (8 + (lane & 15)) * A1_KVP + 160 + (lane >> 4) * 16 + 16 * j);
        const bool up0 = 2 * t > g, up1 = 2 * t + 1 > g, edge = (mb | (warp & 3)) == 0;
        float rk[4];
        auto above = [&]() {
            mbar_wait(bar_kv + 8 * warp, 0);
#pragma unroll
            for (int j = 0; j < 12; j += 4) ldsm_x4(&kp[j], mrow + 16 * j);
            rk[0] = rw[2 * t - (up0 ? 8 : 0)].y; rk[1] = rw[2 * t + 1 - (up1 ? 8 : 0)].y;
#pragma unroll
            for (int j = 0; j < 12; j += 4) ldsm_x4_t(&vp[j], mrow + 160 + 16 * j - (j == 8 ? (lane & 16) * 2 : 0));
            __syncwarp();
            if (lane == 0) mbar_arrive(bar_kvf);
        };
        auto halo = [&]() {
            if (lane == 0) mbar_arrive(bar_kvf);
            const uint4* hin = g_halo + (((layer * 16 + mb - 1) * 8 + hg) * 2 + wg) * 168;
            uint32_t hv[22] = {};
            rk[0] = rw[2 * t].y; rk[1] = rw[2 * t + 1].y;
            if (mb > 0) {
#pragma unroll 1
                for (int it = 0; it < SPIN_MAX; it++) {
#pragma unroll
                    for (int k = 0; k < 20; k += 4)
                        asm volatile("ld.relaxed.gpu.global.v4.u32 {%0,%1,%2,%3}, [%4];" : "=r"(hv[k]), "=r"(hv[k + 1]), "=r"(hv[k + 2]), "=r"(hv[k + 3]) : "l"(hin + 8 * k + lane) : "memory");
                    asm volatile("ld.relaxed.gpu.global.v2.u32 {%0,%1}, [%2];" : "=r"(hv[20]), "=r"(hv[21]) : "l"(reinterpret_cast<const uint2*>(hin + 160) + t) : "memory");
                    uint32_t m = max(hv[20], hv[21]);
#pragma unroll
                    for (int k = 0; k < 20; k += 2) m = __vimax3_u32(m, hv[k], hv[k + 1]);
                    if (!__any_sync(~0u, m == ~0u)) break;
                }
            }
            if (tid == 0) mbar_arrive(bars + 144);
            if (lane == 0) DBGC(52 - 16 * wg);
#pragma unroll
            for (int j = 0; j < 10; j++) {
                kp[j] = hv[j];
                asm volatile("movmatrix.sync.aligned.m8n8.trans.b16 %0, %1;" : "=r"(vp[j]) : "r"(hv[10 + j]));
            }
            if (up0) rk[0] = __uint_as_float(hv[20]);
            if (up1) rk[1] = __uint_as_float(hv[21]);
        };
        rk[2] = rw[2 * t + (up0 ? 0 : 8)].y; rk[3] = rw[2 * t + 1 + (up1 ? 0 : 8)].y;
        uint32_t qs[4][2];
#pragma unroll
        for (int h = 0; h < 4; h++) {
            qs[h][0] = (t >> 1) == (h & 1) ? f[0][5 * (h >> 1) + 2] : 0u; qs[h][1] = (t >> 1) == (h & 1) ? f[1][5 * (h >> 1) + 2] : 0u;
            asm volatile("" : "+r"(qs[h][0]), "+r"(qs[h][1]));
        }
#pragma unroll
        for (int j = 0; j < 10; j++) asm volatile("" : "+r"(f[0][j]), "+r"(f[1][j]), "+r"(f[0][10 + j]));
        if (warp & 3) above(); else if (wg) halo();
        TSTAMP1T(10, 64);
        float sc[4][3][4];
#pragma unroll
        for (int h = 0; h < 4; h++) {
            const int jb = 5 * (h >> 1) + 3 * (h & 1), js = 5 * (h >> 1) + 2;
#pragma unroll
            for (int nt = 1; nt < 3; nt++) {
#pragma unroll
                for (int e = 0; e < 4; e++) sc[h][nt][e] = 0.f;
                mma_bf16(sc[h][nt], f[0][jb], f[1][jb], f[0][jb + 1], f[1][jb + 1], f[nt - 1][10 + jb], f[nt - 1][11 + jb]);
                mma_bf16_k8(sc[h][nt], qs[h][0], qs[h][1], f[nt - 1][10 + js]);
            }
        }
        if (tid == 128) mbar_arrive(bars + 240);
        if (warp == 0) halo();
        TSTAMP1(8);
#pragma unroll
        for (int h = 0; h < 4; h++) {
            const int jb = 5 * (h >> 1) + 3 * (h & 1), js = 5 * (h >> 1) + 2;
#pragma unroll
            for (int e = 0; e < 4; e++) sc[h][0][e] = 0.f;
            mma_bf16(sc[h][0], f[0][jb], f[1][jb], f[0][jb + 1], f[1][jb + 1], kp[jb], kp[jb + 1]);
            mma_bf16_k8(sc[h][0], qs[h][0], qs[h][1], kp[js]);
        }
        if (warp > 4) { __syncwarp(); if (lane == 0) mbar_arrive(bars + 240); }
        TSTAMP1T(3, 64);
        float p[4][4], sum[4][2];
        uint32_t lg[4][2], mx[4];
        const float rl[4] = {rk[0] * ra, rk[1] * ra, rk[2] * rb, rk[3] * rb};
        auto max2 = [](uint32_t a, uint32_t b) { uint32_t r; asm("max.bf16x2 %0, %1, %2;" : "=r"(r) : "r"(a), "r"(b)); return r; };
#pragma unroll
        for (int h = 0; h < 4; h++) {
            lg[h][0] = pack2((up0 ? sc[h][0][0] : sc[h][1][0]) * rl[0], (up0 ? sc[h][1][2] : sc[h][2][2]) * rl[2]);
            lg[h][1] = pack2((up1 ? sc[h][0][1] : sc[h][1][1]) * rl[1], (up1 ? sc[h][1][3] : sc[h][2][3]) * rl[3]);
            if (edge) {
                if (up0) lg[h][0] = __byte_perm(lg[h][0], 0xce6eu, 0x3254);
                if (up1) lg[h][1] = __byte_perm(lg[h][1], 0xce6eu, 0x3254);
            }
            mx[h] = max2(lg[h][0], lg[h][1]);
        }
#pragma unroll
        for (int o = 1; o <= 2; o <<= 1)
#pragma unroll
            for (int h = 0; h < 4; h++) mx[h] = max2(mx[h], __shfl_xor_sync(~0u, mx[h], o));
#pragma unroll
        for (int h = 0; h < 4; h++)
#pragma unroll
            for (int r = 0; r < 2; r++) {
                const float m = __uint_as_float(r ? mx[h] & 0xffff0000u : mx[h] << 16);
#pragma unroll
                for (int e = 0; e < 2; e++)
                    asm("ex2.approx.ftz.f32 %0, %1;" : "=f"(p[h][2 * r + e]) : "f"((__uint_as_float(r ? lg[h][e] & 0xffff0000u : lg[h][e] << 16) - m) * 1.4426950408889634f));
                sum[h][r] = p[h][2 * r] + p[h][2 * r + 1];
            }
#pragma unroll
        for (int o = 1; o <= 2; o <<= 1)
#pragma unroll
            for (int h = 0; h < 4; h++)
#pragma unroll
                for (int r = 0; r < 2; r++) sum[h][r] += __shfl_xor_sync(~0u, sum[h][r], o);
        TSTAMP1T(5, 64);
        const uint32_t mu = (up0 ? 0xffffu : 0u) | (up1 ? 0xffff0000u : 0u);
        uint32_t ob[10][2];
#pragma unroll
        for (int P = 0; P < 2; P++) {
            float os[2][4];
#pragma unroll
            for (int e = 0; e < 2; e++) {
                const int h = 2 * P + e;
                const float i0 = rcp_apx(sum[h][0]), i1 = rcp_apx(sum[h][1]);
                const uint32_t w0 = pack2(p[h][0] * rk[0] * i0, p[h][1] * rk[1] * i0), w1 = pack2(p[h][2] * rk[2] * i1, p[h][3] * rk[3] * i1);
#pragma unroll
                for (int dt = 0; dt < 3; dt++) {
                    const int j = 5 * P + (dt < 2 ? 3 * e + dt : 2);
                    float o[4] = {0.f, 0.f, 0.f, 0.f};
                    mma_bf16(o, w0 & ~mu, w1 & mu, 0u, w1 & ~mu, vb[j][0], vb[j][1]);
                    mma_bf16_k8(o, w0 & mu, 0u, vp[j]);
                    if (dt < 2) { ob[j][0] = pack2(o[0], o[1]); ob[j][1] = pack2(o[2], o[3]); }
                    else { os[e][0] = o[0]; os[e][1] = o[1]; os[e][2] = o[2]; os[e][3] = o[3]; }
                }
            }
#pragma unroll
            for (int k = 0; k < 4; k++) os[0][k] = t < 2 ? os[0][k] : os[1][k];
            ob[5 * P + 2][0] = pack2(os[0][0], os[0][1]); ob[5 * P + 2][1] = pack2(os[0][2], os[0][3]);
        }
        const uint32_t sl = sbase + (wg ? A1_SM_A1 : A1_SM_A0);
        const uint32_t o0 = (warp & 3) * 2048 + g * 64 + ((t ^ (g >> 1)) << 4), o1 = 8192 + (warp & 3) * 512 + g * 32 + ((t ^ ((g >> 2) << 1)) << 3);
        mbar_wait(bar_done, 0);
        if (wg == 0) mbar_wait(bar_kvf, 0);
#pragma unroll
        for (int h = 0; h < 2; h++) {
            asm volatile("st.shared.v4.u32 [%0], {%1,%2,%3,%4};" ::"r"(sl + o0 + h * 1024), "r"(ob[0][h]), "r"(ob[1][h]), "r"(ob[2][h]), "r"(ob[3][h]) : "memory");
            asm volatile("st.shared.v4.u32 [%0], {%1,%2,%3,%4};" ::"r"(sl + o0 + h * 1024 + 512), "r"(ob[4][h]), "r"(ob[5][h]), "r"(ob[6][h]), "r"(ob[7][h]) : "memory");
            asm volatile("st.shared.v2.u32 [%0], {%1,%2};" ::"r"(sl + o1 + h * 256), "r"(ob[8][h]), "r"(ob[9][h]) : "memory");
        }
        fence_async_smem();
        __syncwarp();
        TSTAMP1T(4, 64);
        TSTAMP1(1);
        TSTAMP2(1);
        const unsigned char* ot = reinterpret_cast<const unsigned char*>(of) + mb * 163840 + wg * 10240;
        if (lane == 0) {
            asm volatile("cp.async.bulk.global.shared::cta.bulk_group [%0], [%1], 2048;" ::"l"(ot + hg * 20480 + (warp & 3) * 2048), "r"(sl + (warp & 3) * 2048) : "memory");
            asm volatile("cp.async.bulk.global.shared::cta.bulk_group [%0], [%1], 512;" ::"l"(ot + hg * 20480 + 8192 + (warp & 3) * 512), "r"(sl + 8192 + (warp & 3) * 512) : "memory");
            asm volatile("cp.async.bulk.commit_group;" ::: "memory");
            if (wg == 0) mbar_arrive(bar_pv);
            asm volatile("cp.async.bulk.wait_group 0;" ::: "memory");
            asm volatile(A1_FRED " [%0], 1;" ::"l"(reinterpret_cast<uint32_t*>(rsum + 2 * SEQ) + (((layer * 16 + mb) * 2 + wg) * 8 + hg) * FSTR) : "memory");
            DBGC(4 + warp);
        }
        TSTAMP4(11);
        float ac2[40];
        const uint64_t db0 = make_desc(sbase, 1024, 256, 3), db1 = make_desc(sbase + 10240, 512, 256, 3), da0 = make_desc(sl, 16, 1024, 2), da1 = make_desc(sl + 8192, 16, 256, 3);
        const uint32_t o7 = wg ? 640 : (A1_SM_W0 - A1_SM_A0) >> 4;
        const uint32_t trow = ((lane & 7) + 8 * (lane >> 4)) * 128 + (((2 * (warp & 3) + ((lane >> 3) & 1)) ^ (lane & 7)) << 4);
        uint32_t xr[10][2];
        mbar_wait(bar_f2 + 64 * wg + 64, 0);
        if (layer == 0) {
#pragma unroll
            for (int j = 0; j < 10; j += 2) ldsm_x4(&xr[j][0], sl + 51200 + (16 * (warp & 3) + (lane & 15)) * 160 + (lane >> 4) * 16 + 16 * j);
        } else {
#pragma unroll
            for (int j = 0; j < 10; j += 2) ldsm_x4_t(&xr[j][0], sl + 51200 + trow + 1024 * j);
        }
        const uint32_t ri = __shfl_sync(~0u, layer * SEQ + (wg * 2 + ((g >> 1) & 1)) * 512 + (mb * 16 + 4 * (warp & 3) + (g >> 2)) * 2 + (g & 1), lane);
        mbar_wait(bar_wo, 0);
        if (wg) mbar_wait(bar_pv, 0);
        if (wg) asm volatile("bar.sync 2, 128;" ::: "memory"); else asm volatile("bar.sync 1, 128;" ::: "memory");
        TSTAMP2(2);
#pragma unroll
        for (int q = 0; q < 8; q++) {
            uint32_t bo = wo_off(0) >> 4;
            if (q) {
                mbar_wait(bar_f2 + 64 * wg + 8 * q, 0);
                asm volatile("ld.shared.u32 %0, [%1];" : "=r"(bo) : "r"(que + 32 * wg + 4 * q) : "memory");
                bo = __shfl_sync(~0u, bo, 0);
                TSTAMP4(q);
                if (q == 1 && (tid & 127) == 0) DBGC(29 + 8 * wg);
            }
            wgmma_fence();
#pragma unroll
            for (int j = 0; j < 5; j++) wgmma_n80(ac2, (j < 4 ? da0 : da1) + (q == 7 ? o7 : 0u) + (uint64_t)((q < 6 ? q * 640 : 0) + (j & 2) * 16 + (j & 1) * 2), (j < 4 ? db0 : db1) + bo + (uint64_t)((j & 2) * 160 + (j & 1) * 32), j || q);
            wgmma_commit();
            if (q == 0) {
                wgmma_wait<0>();
                if ((tid & 127) == 0) { mbar_arrive(bar_e2 + 16 * wg); mbar_arrive(bar_e2 + 8); }
            }
            if (q == 2 && wg) {
                wgmma_wait<1>();
                if (tid == 128) mbar_arrive(bar_e2 + 24);
            }
        }
        if ((tid & 127) == 0) DBGC(28 + wg * 8 + 7);
        TSTAMP2(3);
        wgmma_wait<0>();
        TSTAMP2(4);
        if (__any_sync(~0u, ac2[0] != ac2[0] || ac2[2] != ac2[2])) {
#pragma unroll
            for (int i = 0; i < 40; i++) ac2[i] = 0.f;
            uint32_t a[20], an[20];
            auto lda = [&](uint32_t (&r)[20], int h) {
#pragma unroll
                for (int u = 0; u < 4; u++)
                    asm volatile("ld.relaxed.gpu.global.v4.u32 {%0,%1,%2,%3}, [%4];" : "=r"(r[4 * u]), "=r"(r[4 * u + 1]), "=r"(r[4 * u + 2]), "=r"(r[4 * u + 3]) : "l"(ot + h * 20480 + o0 + u * 512) : "memory");
#pragma unroll
                for (int u = 0; u < 2; u++)
                    asm volatile("ld.relaxed.gpu.global.v2.u32 {%0,%1}, [%2];" : "=r"(r[16 + 2 * u]), "=r"(r[17 + 2 * u]) : "l"(ot + h * 20480 + o1 + u * 256) : "memory");
            };
            lda(an, 0);
#pragma unroll 5
            for (int k = lane; k < WOB / 16; k += 32)
                reinterpret_cast<uint4*>(stg + (sl - sbase))[k] = __ldcg(reinterpret_cast<const uint4*>(wo + hg * 8 * WOB) + k);
            __syncwarp();
#pragma unroll 1
            for (int h = 0; h < 8; h++) {
#pragma unroll 1
                for (int it = 0; it < SPIN_MAX; it++) {
                    uint32_t m = 0;
#pragma unroll
                    for (int k = 0; k < 20; k += 2) m = __vimax3_u32(m, an[k], an[k + 1]);
                    if (!__any_sync(~0u, m == ~0u)) break;
                    lda(an, h);
                }
#pragma unroll
                for (int k = 0; k < 20; k++) a[k] = an[k];
                lda(an, min(h + 1, 7));
                const uint32_t bp = h == hg ? sl : sbase + wo_off(h + (h < hg));
                const int r0 = 8 * ((lane & 7) >> 1) + 2 * (lane >> 3) + (lane & 1), r2 = 4 * ((lane & 7) >> 1) + 2 * ((lane >> 3) & 1) + (lane & 1);
#pragma unroll
                for (int n = 0; n < 10; n++) {
                    uint32_t b[12];
                    ldsm_x4_t(b, bp + (n >> 1) * 1024 + r0 * 32 + (((n ^ (r0 >> 2)) & 1) << 4));
                    ldsm_x4_t(b + 4, bp + 5120 + (n >> 1) * 1024 + r0 * 32 + (((n ^ (r0 >> 2)) & 1) << 4));
                    ldsm_x4_t(b + 8, bp + 10240 + (n >> 1) * 512 + r2 * 32 + (((n ^ (r2 >> 2)) & 1) << 4));
                    mma_bf16(ac2 + 4 * n, a[0], a[8], a[1], a[9], b[0], b[1]); mma_bf16(ac2 + 4 * n, a[2], a[10], a[3], a[11], b[2], b[3]);
                    mma_bf16(ac2 + 4 * n, a[4], a[12], a[5], a[13], b[4], b[5]); mma_bf16(ac2 + 4 * n, a[6], a[14], a[7], a[15], b[6], b[7]);
                    mma_bf16(ac2 + 4 * n, a[16], a[18], a[17], a[19], b[8], b[9]);
                }
            }
        }
#pragma unroll
        for (int j = 0; j < 10; j++)
#pragma unroll
            for (int hh = 0; hh < 2; hh++) {
                const uint32_t a = pack2(ac2[4 * j + 2 * hh], ac2[4 * j + 2 * hh + 1]);
                const __nv_bfloat162 r = __hadd2_rn(*reinterpret_cast<const __nv_bfloat162*>(&xr[j][hh]), *reinterpret_cast<const __nv_bfloat162*>(&a));
                xr[j][hh] = *reinterpret_cast<const uint32_t*>(&r);
            }
        const uint32_t so = sl + 30720;
#pragma unroll
        for (int j = 0; j < 10; j += 2) stsm_x4_t(so + trow + 1024 * j, xr[j][0], xr[j][1], xr[j + 1][0], xr[j + 1][1]);
        fence_async_smem();
        if (wg) asm volatile("bar.sync 2, 128;" ::: "memory"); else asm volatile("bar.sync 1, 128;" ::: "memory");
        TSTAMP2(5);
        if ((tid & 127) == 0) {
            asm volatile("cp.async.bulk.tensor.2d.global.shared::cta.bulk_group [%0, {%1, %2}], [%3];" ::"l"(&tmX1), "r"(mb * 128 + 64 * wg), "r"(hg * 80), "r"(so) : "memory");
            asm volatile("cp.async.bulk.commit_group;" ::: "memory");
        }
        __syncwarp();
        const float p0 = *(volatile const float*)&rw[g].x, p1 = *(volatile const float*)&rw[g + 8].x;
        float s[3][4] = {};
        const uint32_t pp[2] = {__byte_perm(__float_as_uint(p0), 0, 0x3232), __byte_perm(__float_as_uint(p1), 0, 0x3232)};
#pragma unroll
        for (int j = 0; j < 10; j += 2) {
            const uint32_t d0 = sub2(xr[j][0], pp[0]), d1 = sub2(xr[j][1], pp[1]), d2 = sub2(xr[j + 1][0], pp[0]), d3 = sub2(xr[j + 1][1], pp[1]);
            mma_bf16(s[0], xr[j][0], xr[j][1], xr[j + 1][0], xr[j + 1][1], 0x3f803f80u, 0x3f803f80u);
            mma_bf16(s[1], d0, d1, d2, d3, d0, d2);
            mma_bf16(s[2], d0, d1, d2, d3, d1, d3);
        }
        if (t == (g >> 1)) {
            float2* rp = rsum + ri;
            asm volatile("red.relaxed.gpu.global.add.v2.f32 [%0], {%1, %2};" ::"l"(rp), "f"(fmaf(-80.f, p0, s[0][0])), "f"((g & 1) ? s[1][1] : s[1][0]) : "memory");
            asm volatile("red.relaxed.gpu.global.add.v2.f32 [%0], {%1, %2};" ::"l"(rp + 4), "f"(fmaf(-80.f, p1, s[0][2])), "f"((g & 1) ? s[2][3] : s[2][2]) : "memory");
        }
        asm volatile("cp.async.bulk.wait_group.read 0;" ::: "memory");
        TSTAMP2(6);
        if (tid == 0) DBGC(63);
        if (tid == 128) DBGC(28);
        if (tid == 0) DBGCAL(2);
        GSTAMP(g_tim1, 14);
        SPAN(1 + 4 * layer, 3);
    }
}

static int h_nsm;
static void* h_sym[11];
static TileTab h_tab;
static CUtensorMap h_tmX0, h_tmX1, h_tmR0, h_tmR1, h_tmX1st, h_tmOut, h_tmWq, h_tmWo, h_tmWt, h_tmWc;
typedef CUresult (*PFN_encodeTiled)(CUtensorMap*, CUtensorMapDataType, cuuint32_t, void*, const cuuint64_t*, const cuuint64_t*,
                                    const cuuint32_t*, const cuuint32_t*, CUtensorMapInterleave, CUtensorMapSwizzle,
                                    CUtensorMapL2promotion, CUtensorMapFloatOOBfill);
static void make_tmap(CUtensorMap* tm, const void* ptr, uint64_t cols, uint64_t rows, uint32_t bc, uint32_t br, CUtensorMapSwizzle sw, uint64_t pitch = 0, uint64_t hi = 0, uint32_t bh = 2) {
    static PFN_encodeTiled fn = nullptr;
    if (!fn) {
        void* p = nullptr; cudaDriverEntryPointQueryResult qr;
        cudaGetDriverEntryPoint("cuTensorMapEncodeTiled", &p, cudaEnableDefault, &qr);
        fn = (PFN_encodeTiled)p;
    }
    if (br == 0) {
        cuuint64_t dims[5] = {16, 2, rows / 8, 4, cols / 16}; cuuint64_t strides[4] = {cols * 2, cols * 16, cols * 4, 32};
        cuuint32_t box[5] = {16, 2, bc, 4, 5}; cuuint32_t es[5] = {1, 1, 1, 1, 1};
        fn(tm, CU_TENSOR_MAP_DATA_TYPE_BFLOAT16, 5, const_cast<void*>(ptr), dims, strides, box, es, CU_TENSOR_MAP_INTERLEAVE_NONE, sw,
           CU_TENSOR_MAP_L2_PROMOTION_L2_128B, CU_TENSOR_MAP_FLOAT_OOB_FILL_NONE);
        return;
    }
    if (bh == 0) {
        cuuint64_t dims[5] = {64, 64, 2, 16, 10}; cuuint64_t strides[4] = {pitch * 2, hi * 2, cols * 2, rows * 2};
        cuuint32_t box[5] = {64, 64, 2, 1, 1}; cuuint32_t es[5] = {1, 1, 1, 1, 1};
        fn(tm, CU_TENSOR_MAP_DATA_TYPE_BFLOAT16, 5, const_cast<void*>(ptr), dims, strides, box, es, CU_TENSOR_MAP_INTERLEAVE_NONE, sw,
           CU_TENSOR_MAP_L2_PROMOTION_L2_128B, CU_TENSOR_MAP_FLOAT_OOB_FILL_NONE);
        return;
    }
    if (hi) {
        cuuint64_t dims[3] = {cols, rows, hi == 64 ? 32u : hi == 16 ? 120u : 2u}; cuuint64_t strides[2] = {pitch * 2, hi * 2};
        cuuint32_t box[3] = {bc, br, bh}; cuuint32_t es[3] = {1, 1, 1};
        fn(tm, CU_TENSOR_MAP_DATA_TYPE_BFLOAT16, 3, const_cast<void*>(ptr), dims, strides, box, es, CU_TENSOR_MAP_INTERLEAVE_NONE, sw,
           CU_TENSOR_MAP_L2_PROMOTION_L2_128B, CU_TENSOR_MAP_FLOAT_OOB_FILL_NONE);
        return;
    }
    cuuint64_t dims[2] = {cols, rows}; cuuint64_t strides[1] = {(pitch ? pitch : cols) * 2};
    cuuint32_t box[2] = {bc, br}; cuuint32_t es[2] = {1, 1};
    fn(tm, CU_TENSOR_MAP_DATA_TYPE_BFLOAT16, 2, const_cast<void*>(ptr), dims, strides, box, es, CU_TENSOR_MAP_INTERLEAVE_NONE, sw,
       CU_TENSOR_MAP_L2_PROMOTION_L2_128B, CU_TENSOR_MAP_FLOAT_OOB_FILL_NONE);
}
template <typename... Args>
static void launch_pdl(void (*kern)(Args...), int grid, int block, int smem, Args... args) {
    cudaLaunchConfig_t cfg = {};
    cfg.gridDim = dim3(grid); cfg.blockDim = dim3(block); cfg.dynamicSmemBytes = smem; cfg.stream = cudaStreamPerThread;
    cudaLaunchAttribute at[1];
    at[0].id = cudaLaunchAttributeProgrammaticStreamSerialization; at[0].val.programmaticStreamSerializationAllowed = 1;
    cfg.attrs = at; cfg.numAttrs = 1;
    cudaLaunchKernelEx(&cfg, kern, args...);
}
static void launch_stage(int k, void* const* d_in, void* d_out) {
    const KgIn kg = {(const bf16*)d_in[4], (const bf16*)d_in[5], (const bf16*)d_in[6], (const bf16*)d_in[7], (const bf16*)d_in[8], (const bf16*)d_in[0], (const bf16*)d_in[1], (const bf16*)d_in[2],
                      (uint4*)h_sym[0], (uint4*)h_sym[1], (uint4*)h_sym[2], (uint4*)h_sym[3], (uint4*)h_sym[4], (float*)h_sym[5]};
    switch (k) {
        case 0: kgen_kernel<<<128, 512, KG_SMEM, cudaStreamPerThread>>>(kg, h_tmWq, h_tmWo, h_tmWt, h_tmWc); break;
        case 1: launch_pdl(a1_kernel, h_nsm, A1_THREADS, A1_SMEM, 0, (const bf16*)d_in[0], (const unsigned char*)h_sym[1], (const unsigned char*)h_sym[2], (float2*)h_sym[4], (uint4*)h_sym[6], h_tmX0, h_tmR0, h_tmX1st, h_tab); break;
        case 3: launch_pdl(conv_kernel, DM / CV_CPB, CV_THREADS, CV_SMEM, (const bf16*)d_in[9], 0, (const uint4*)h_sym[7], (const float4*)h_sym[4], (const bf16*)h_sym[8], (bf16*)h_sym[9], (const uint4*)h_sym[0], (bf16*)h_sym[10], h_tmOut); break;
        case 5: launch_pdl(a1_kernel, h_nsm, A1_THREADS, A1_SMEM, 1, (const bf16*)d_in[0], (const unsigned char*)h_sym[1], (const unsigned char*)h_sym[2], (float2*)h_sym[4], (uint4*)h_sym[6], h_tmX1, h_tmR1, h_tmX1st, h_tab); break;
        case 7: launch_pdl(conv_kernel, DM / CV_CPB, CV_THREADS, CV_SMEM, (const bf16*)d_in[9], 1, (const uint4*)h_sym[7] + SEQ / 8, (const float4*)h_sym[4] + SEQ / 2, (const bf16*)h_sym[8], (bf16*)h_sym[10], (const uint4*)h_sym[0], (bf16*)h_sym[10], h_tmOut); break;
        default: break;
    }
}
static int n_stage_kernels() { return 9; }
static const char* stage_name(int k) { const char* n[] = {"kgen", "a1", "a2", "conv", "tr", "a1", "a2", "conv", "tr"}; return n[k]; }

extern "C" void kernel_launch(void* const* d_in, const int* in_sizes, int n_in, void* d_out, int out_size) {
    (void)in_sizes; (void)n_in; (void)out_size;
    static const void *p_in = nullptr, *p_w1 = nullptr, *p_w2 = nullptr, *p_out = nullptr;
    if (p_in != d_in[0] || p_w1 != d_in[1] || p_w2 != d_in[2] || p_out != d_out) {
        cudaFuncSetAttribute(conv_kernel, cudaFuncAttributeMaxDynamicSharedMemorySize, CV_SMEM);
        cudaFuncSetAttribute(kgen_kernel, cudaFuncAttributeMaxDynamicSharedMemorySize, KG_SMEM);
        cudaFuncSetAttribute(a1_kernel, cudaFuncAttributeMaxDynamicSharedMemorySize, A1_SMEM);
        int dev; cudaGetDevice(&dev); cudaDeviceGetAttribute(&h_nsm, cudaDevAttrMultiProcessorCount, dev);
        if (h_nsm != 132) h_nsm = 128;
        h_tab.ns = h_nsm == 132 ? 132 : ~0u;
        for (int i = 0; i < 264; i++) {
            const int h = (i - 64) >> 1;
            const int t = i >= 132 ? i - 132 : i < 64 ? ((i >> 1) & 7) * 16 + (i >> 4) * 2 + (i & 1) : i < 120 ? (1 + h % 7) * 16 + 8 + (h / 7) * 2 + (i & 1) : i < 124 ? 128 : i - 116;
            const int hg = (4 * (t >> 6) + (t & 3)) & 7;
            h_tab.e[i] = {(unsigned char)((t >> 2) & 15), (unsigned char)hg, (unsigned char)(5 * (hg >> 2)), (unsigned char)t, (uint32_t)(hg * 10 * WQ_STAGE)};
        }
        cudaGetSymbolAddress(&h_sym[0], g_tap); cudaGetSymbolAddress(&h_sym[1], g_wq); cudaGetSymbolAddress(&h_sym[2], g_wo);
        cudaGetSymbolAddress(&h_sym[3], g_halo); cudaGetSymbolAddress(&h_sym[4], g_sum); cudaGetSymbolAddress(&h_sym[5], g_csp); cudaGetSymbolAddress(&h_sym[6], g_of);
        cudaGetSymbolAddress(&h_sym[7], g_piv); cudaGetSymbolAddress(&h_sym[8], g_x1T); cudaGetSymbolAddress(&h_sym[9], g_xcT); cudaGetSymbolAddress(&h_sym[10], g_yT);
        void *px1, *px2;
        cudaGetSymbolAddress(&px1, g_x1T); cudaGetSymbolAddress(&px2, g_xcT);
        make_tmap(&h_tmX0, d_in[0], 128 * 640, 64, 64, 64, CU_TENSOR_MAP_SWIZZLE_128B, 1280, 640, 0);
        make_tmap(&h_tmX1, px2, 128, 64 * XCP, 64, 64, CU_TENSOR_MAP_SWIZZLE_128B, XCP, 64, 0);
        make_tmap(&h_tmR0, d_in[0], 640, 1024, 80, 64, CU_TENSOR_MAP_SWIZZLE_NONE, 1280, 640, 1);
        make_tmap(&h_tmR1, px2, 64, 640, 64, 80, CU_TENSOR_MAP_SWIZZLE_128B, XCP, 64, 1);
        make_tmap(&h_tmX1st, px1, 2048, 640, 64, 80, CU_TENSOR_MAP_SWIZZLE_128B, XCP);
        make_tmap(&h_tmWq, d_in[1], 16, 640, 16, 32, CU_TENSOR_MAP_SWIZZLE_32B, 1920, 16, 5);
        make_tmap(&h_tmWc, d_in[1], 16, 640, 16, 64, CU_TENSOR_MAP_SWIZZLE_32B, 1920, 16, 1);
        make_tmap(&h_tmWo, d_in[2], 640, 640, 4, 0, CU_TENSOR_MAP_SWIZZLE_32B);
        make_tmap(&h_tmWt, d_in[2], 640, 640, 2, 0, CU_TENSOR_MAP_SWIZZLE_32B);
        make_tmap(&h_tmOut, d_out, 640, 2048, 80, 8, CU_TENSOR_MAP_SWIZZLE_NONE);
        p_in = d_in[0]; p_w1 = d_in[1]; p_w2 = d_in[2]; p_out = d_out;
    }
    for (int k = 0; k < n_stage_kernels(); k++) launch_stage(k, d_in, d_out);
}
```

```cpp
#include <cuda_runtime.h>
#include <cuda_bf16.h>
#include <stdint.h>
#include <cuda.h>

typedef __nv_bfloat16 bf16;

constexpr int SEQ = 2048;
constexpr int DM = 640;
constexpr int NMODE = 192;

__device__ __forceinline__ float bf2f(bf16 v) { return __bfloat162float(v); }
__device__ __forceinline__ float rbf(float v) {
    uint32_t r;
    asm("cvt.rn.bf16x2.f32 %0, %1, %2;" : "=r"(r) : "f"(v), "f"(0.f));
    return __uint_as_float(r);
}
__device__ __forceinline__ uint32_t pack2(float lo, float hi) {
    __nv_bfloat162 t = __floats2bfloat162_rn(lo, hi);
    return *reinterpret_cast<uint32_t*>(&t);
}
__device__ __forceinline__ void pdl_sync() {
    asm volatile("griddepcontrol.wait;" ::: "memory");
    asm volatile("griddepcontrol.launch_dependents;" ::: "memory");
}
__device__ __forceinline__ float sqrt_apx(float v) { float r; asm("sqrt.approx.ftz.f32 %0, %1;" : "=f"(r) : "f"(v)); return r; }
__device__ __forceinline__ float rcp_apx(float v) { float r; asm("rcp.approx.ftz.f32 %0, %1;" : "=f"(r) : "f"(v)); return r; }
__device__ __forceinline__ uint32_t smem_u32(const void* p) { return (uint32_t)__cvta_generic_to_shared(p); }

constexpr int TPAD = 16;
constexpr int DLEN = 544;
constexpr int TAP_W2 = DLEN * 8, TAP_W3 = TAP_W2 + 768, TAP_C = TAP_W3 + 768, TAPB = TAP_C + 384;
__device__ __align__(128) uint4 g_tap[DM * 128];
#define XPAD 64
constexpr int XCP = SEQ + XPAD;
__device__ __align__(128) bf16 g_x1T[DM * XCP];
__device__ __align__(128) bf16 g_xcT[DM * XCP];
__device__ __align__(128) uint4 g_of[128 * 1280];
constexpr int WQ_STAGE = 240 * 128, WOB = 80 * 160;
__device__ __align__(128) uint4 g_wq[8 * 10 * WQ_STAGE / 16];
__device__ __align__(128) uint4 g_wo[64 * WOB / 16];
__device__ __align__(16) float g_csp[10 * 1920];
#define FSTR 32
__device__ __align__(128) float2 g_sum[2 * SEQ + 256 * FSTR];
__device__ __align__(16) bf16 g_piv[2 * SEQ];
__device__ __align__(128) bf16 g_yT[DM * XCP];
__device__ uint32_t g_epoch;
__device__ __align__(16) unsigned long long g_rstat[SEQ];
__device__ __align__(128) uint4 g_halo[640 * 148];
__device__ __forceinline__ unsigned long long tagw(uint32_t payload, uint32_t tag) { return ((unsigned long long)tag << 32) | payload; }
__device__ __forceinline__ ulonglong2 ld_tag2(const ulonglong2* p) {
    ulonglong2 v;
    asm volatile("ld.relaxed.gpu.global.v2.u64 {%0, %1}, [%2];" : "=l"(v.x), "=l"(v.y) : "l"(p) : "memory");
    return v;
}
__device__ __forceinline__ bool tag_ok(ulonglong2 v, uint32_t tag) { return (uint32_t)(v.x >> 32) == tag && (uint32_t)(v.y >> 32) == tag; }
__device__ __forceinline__ uint32_t ld_epoch() { uint32_t v; asm volatile("ld.relaxed.gpu.global.u32 %0, [%1];" : "=r"(v) : "l"(&g_epoch) : "memory"); return v + 1; }
constexpr int SPIN_MAX = 1 << 20;
__device__ uint32_t g_started[4];
__device__ __forceinline__ void sm_started(int slot) { asm volatile("red.relaxed.gpu.global.add.u32 [%0], 1;" ::"l"(g_started + slot) : "memory"); }
__device__ __noinline__ void sm_idle(int slot) {
    if (threadIdx.x) return;
    sm_started(slot);
    const uint32_t want = ld_epoch() * gridDim.x;
    pdl_sync();
#pragma unroll 1
    for (int it = 0; it < SPIN_MAX; it++) {
        uint32_t v;
        asm volatile("ld.relaxed.gpu.global.u32 %0, [%1];" : "=r"(v) : "l"(g_started + slot) : "memory");
        if ((int)(v - want) >= 0) break;
        __nanosleep(100);
    }
}
struct TileTab { uint32_t ns, pad; struct { unsigned char mb, hg, kb0, tile; uint32_t woff; } __align__(8) e[264]; };
__device__ __forceinline__ bool elect() {
    uint32_t p;
    asm volatile("{\n.reg .pred p;\nelect.sync _|p, 0xffffffff;\nselp.b32 %0, 1, 0, p;\n}" : "=r"(p));
    return p;
}
#define DBG_SYMS
#define TSTAMP(i)
#define TSTAMP1(i)
#define TSTAMP1T(i, t)
#define TSTAMP1X(i, t)
#define SPAN(k, i)
#define GSTAMP(arr, i)
#define TSTAMP2(i)
#define TSTAMP3(i)
#define TSTAMP4(i)
#define TSTAMPK(i, t)
#define DBGC(i)
#define DBGV(i, v)
#define DBGCAL(i)

__device__ __forceinline__ void mma_bf16(float* d, uint32_t a0, uint32_t a1, uint32_t a2, uint32_t a3, uint32_t b0, uint32_t b1) {
    asm volatile("mma.sync.aligned.m16n8k16.row.col.f32.bf16.bf16.f32 {%0,%1,%2,%3}, {%4,%5,%6,%7}, {%8,%9}, {%0,%1,%2,%3};"
                 : "+f"(d[0]), "+f"(d[1]), "+f"(d[2]), "+f"(d[3]) : "r"(a0), "r"(a1), "r"(a2), "r"(a3), "r"(b0), "r"(b1));
}
__device__ __forceinline__ void mma_bf16_k8(float* d, uint32_t a0, uint32_t a1, uint32_t b0) {
    asm volatile("mma.sync.aligned.m16n8k8.row.col.f32.bf16.bf16.f32 {%0,%1,%2,%3}, {%4,%5}, {%6}, {%0,%1,%2,%3};"
                 : "+f"(d[0]), "+f"(d[1]), "+f"(d[2]), "+f"(d[3]) : "r"(a0), "r"(a1), "r"(b0));
}
__device__ __forceinline__ void ldsm_x4(uint32_t* r, uint32_t addr) {
    asm volatile("ldmatrix.sync.aligned.m8n8.x4.shared.b16 {%0,%1,%2,%3}, [%4];"
                 : "=r"(r[0]), "=r"(r[1]), "=r"(r[2]), "=r"(r[3]) : "r"(addr));
}

__device__ __forceinline__ void ldsm_x4_t(uint32_t* r, uint32_t addr) {
    asm volatile("ldmatrix.sync.aligned.m8n8.x4.trans.shared.b16 {%0,%1,%2,%3}, [%4];"
                 : "=r"(r[0]), "=r"(r[1]), "=r"(r[2]), "=r"(r[3]) : "r"(addr));
}
__device__ __forceinline__ void mbar_init(uint32_t bar, int count) { asm volatile("mbarrier.init.shared::cta.b64 [%0], %1;" ::"r"(bar), "r"(count)); }
__device__ __forceinline__ void mbar_arrive(uint32_t bar) { asm volatile("mbarrier.arrive.shared::cta.b64 _, [%0];" ::"r"(bar) : "memory"); }
__device__ __forceinline__ void mbar_wait(uint32_t bar, uint32_t parity) {
    asm volatile("{\n.reg .pred p;\nWAIT_LOOP:\n"
                 "mbarrier.try_wait.parity.shared::cta.b64 p, [%0], %1;\n"
                 "@p bra.uni WAIT_DONE;\nbra.uni WAIT_LOOP;\nWAIT_DONE:\n}" ::"r"(bar), "r"(parity) : "memory");
}

__device__ __forceinline__ void mbar_expect_tx(uint32_t bar, uint32_t bytes) {
    asm volatile("mbarrier.arrive.expect_tx.shared::cta.b64 _, [%0], %1;" ::"r"(bar), "r"(bytes) : "memory");
}
__device__ __forceinline__ void tma_load_2d(uint32_t dst, const void* tmap, int c0, int c1, uint32_t bar) {
    asm volatile("cp.async.bulk.tensor.2d.shared::cluster.global.mbarrier::complete_tx::bytes [%0], [%1, {%3, %4}], [%2];"
                 ::"r"(dst), "l"(tmap), "r"(bar), "r"(c0), "r"(c1) : "memory");
}
__device__ __forceinline__ void tma_load_3d(uint32_t dst, const void* tmap, int c0, int c1, int c2, uint32_t bar) {
    asm volatile("cp.async.bulk.tensor.3d.shared::cluster.global.mbarrier::complete_tx::bytes [%0], [%1, {%3, %4, %5}], [%2];"
                 ::"r"(dst), "l"(tmap), "r"(bar), "r"(c0), "r"(c1), "r"(c2) : "memory");
}
__device__ __forceinline__ void fence_async_smem() { asm volatile("fence.proxy.async.shared::cta;" ::: "memory"); }
__device__ __forceinline__ void bulk_load(uint32_t dst, const void* src, uint32_t bytes, uint32_t bar) {
    asm volatile("cp.async.bulk.shared::cluster.global.mbarrier::complete_tx::bytes [%0], [%1], %2, [%3];"
                 ::"r"(dst), "l"(src), "r"(bytes), "r"(bar) : "memory");
}
__device__ __forceinline__ void tma_store_2d(const void* tmap, int c0, int c1, uint32_t src) {
    asm volatile("cp.async.bulk.tensor.2d.global.shared::cta.bulk_group [%0, {%1, %2}], [%3];" ::"l"(tmap), "r"(c0), "r"(c1), "r"(src) : "memory");
    asm volatile("cp.async.bulk.commit_group;" ::: "memory");
    asm volatile("cp.async.bulk.wait_group.read 0;" ::: "memory");
}
__device__ __forceinline__ void stsm_x4(uint32_t addr, uint32_t r0, uint32_t r1, uint32_t r2, uint32_t r3) {
    asm volatile("stmatrix.sync.aligned.m8n8.x4.shared.b16 [%0], {%1,%2,%3,%4};" ::"r"(addr), "r"(r0), "r"(r1), "r"(r2), "r"(r3) : "memory");
}
__device__ __forceinline__ void stsm_x4_t(uint32_t addr, uint32_t r0, uint32_t r1, uint32_t r2, uint32_t r3) {
    asm volatile("stmatrix.sync.aligned.m8n8.x4.trans.shared.b16 [%0], {%1,%2,%3,%4};" ::"r"(addr), "r"(r0), "r"(r1), "r"(r2), "r"(r3) : "memory");
}
__device__ __forceinline__ void prefetch_tmap(const void* tmap) { asm volatile("prefetch.tensormap [%0];" ::"l"(tmap) : "memory"); }

__device__ __forceinline__ float2 cexp_at(float wr2, float wi, float p) {
    float er;
    asm("ex2.approx.ftz.f32 %0, %1;" : "=f"(er) : "f"(wr2 * p));
    float th = wi * p;
    const float k = rintf(th * 0.15915494309189535f);
    th = fmaf(k, -6.2831854820251465f, th);
    th = fmaf(k, 1.7484555314695172e-7f, th);
    return make_float2(er * __cosf(th), er * __sinf(th));
}
__device__ __forceinline__ float2 cmul(float2 a, float2 b) {
    return make_float2(fmaf(a.x, b.x, -a.y * b.y), fmaf(a.x, b.y, a.y * b.x));
}
__device__ __forceinline__ float2 csqr(float2 a) { return make_float2(fmaf(a.x, a.x, -a.y * a.y), (a.x + a.x) * a.y); }
__device__ __forceinline__ uint32_t packh(float2 v) {
    uint32_t r;
    asm("cvt.rn.f16x2.f32 %0, %1, %2;" : "=r"(r) : "f"(v.y), "f"(v.x));
    return r;
}
__device__ __forceinline__ void mma_f16(float* d, uint32_t a0, uint32_t a1, uint32_t a2, uint32_t a3, uint32_t b0, uint32_t b1) {
    asm volatile("mma.sync.aligned.m16n8k16.row.col.f32.f16.f16.f32 {%0,%1,%2,%3}, {%4,%5,%6,%7}, {%8,%9}, {%0,%1,%2,%3};"
                 : "+f"(d[0]), "+f"(d[1]), "+f"(d[2]), "+f"(d[3]) : "r"(a0), "r"(a1), "r"(a2), "r"(a3), "r"(b0), "r"(b1));
}

struct KgIn { const bf16 *logA, *Aim, *Cre, *Cim, *logdt, *x, *wqkv, *wo; uint4 *tap, *wq, *wop, *halo, *sum; float* csp; };
constexpr int KG_THREADS = NMODE / 2;

constexpr int KG_BUF = 15 * 12288, KG_BAR = KG_BUF + 6 * 5120, KG_SMEM = KG_BAR + 64;
__global__ void __launch_bounds__(512, 1) kgen_kernel(const KgIn in, const __grid_constant__ CUtensorMap tmWq, const __grid_constant__ CUtensorMap tmWo,
                                                        const __grid_constant__ CUtensorMap tmWt) {
    extern __shared__ __align__(1024) uint4 tabs[];
#define KG_ROT 0
    const int lane = threadIdx.x & 31, w16 = (__shfl_sync(~0u, threadIdx.x >> 5, 0) + KG_ROT) & 15, grp = w16 / 3, warp = w16 - 3 * grp;
    const int d = blockIdx.x * 5 + grp, tid = warp * 32 + lane;
    uint4* tab = tabs + grp * (3 * 768);
    SPAN(0, 0); SPAN(0, 1);
    TSTAMPK(0, 0);
    asm volatile("griddepcontrol.launch_dependents;" ::: "memory");
    if (w16 == 15) {
        const uint32_t b0 = smem_u32(tab), wbar = b0 + 6 * 5120;
        const int blk = blockIdx.x, nq = blk < 112 ? 4 : 2, nj = nq + (blk < 64 ? 1 : 2);
        auto fetch = [&](int i) {
            const uint32_t dst = b0 + i * 5120, bar = wbar + 8 * i;
            if (i < nq) {
                const int p = blk + 64 * (i & 2), kb = p / 24;
                mbar_expect_tx(bar, 5120);
                tma_load_3d(dst, &tmWq, 0, kb * 64 + (i & 1) * 32, (p - 24 * kb) * 5, bar);
            } else if (i < nj) {
                const int o = i == nq ? blk : 255 - blk;
                mbar_expect_tx(bar, o < 128 ? 5120 : 2560);
                asm volatile("cp.async.bulk.tensor.5d.shared::cluster.global.mbarrier::complete_tx::bytes [%0], [%1, {%3, %3, %4, %3, %5}], [%2];"
                             ::"r"(dst), "l"(o < 128 ? &tmWo : &tmWt), "r"(bar), "r"(0), "r"((o & 7) * 10 + (o >> 6) * 4), "r"(((o >> 3) & 7) * 5) : "memory");
            }
        };
        const bool one = elect();
        if (one) {
#pragma unroll
            for (int i = 0; i < 6; i++) mbar_init(wbar + 8 * i, 1);
            asm volatile("fence.mbarrier_init.release.cluster;" ::: "memory");
#pragma unroll
            for (int i = 0; i < 6; i++) fetch(i);
        }
        __syncwarp();
#pragma unroll
        for (int i = 1; i <= 5; i++) asm volatile("bar.arrive %0, 128;" ::"r"(i) : "memory");
        if (one) {
#pragma unroll 1
            for (int i = 0; i < nj; i++) {
                const int p = blk + 64 * (i & 2), kb = p / 24, hg = p & 7, sec = (p - 24 * kb) >> 3, o = i == nq ? blk : 255 - blk, cg = (o >> 3) & 7, hb = o & 7;
                const unsigned char* dst = i < nq ? reinterpret_cast<unsigned char*>(in.wq) + (hg * 10 + (hg < 4 ? kb : kb < 5 ? kb + 5 : kb - 5)) * WQ_STAGE + ((i & 1) * 3 + sec) * 5120
                                                  : reinterpret_cast<unsigned char*>(in.wop) + (cg * 8 + (hb == cg ? 0 : hb + (hb < cg))) * WOB + (o >> 6) * 5120;
                mbar_wait(wbar + 8 * i, 0);
                if (i == 0) TSTAMPK(2, (15 - KG_ROT) * 32);
                if (i == 3) TSTAMPK(5, (15 - KG_ROT) * 32);
                asm volatile("cp.async.bulk.global.shared::cta.bulk_group [%0], [%1], %2;" ::"l"(dst), "r"(b0 + i * 5120), "r"(i < nq || o < 128 ? 5120 : 2560) : "memory");
            }
            asm volatile("cp.async.bulk.commit_group;" ::: "memory");
            asm volatile("cp.async.bulk.wait_group.read 0;" ::: "memory");
        }
        TSTAMPK(11, (15 - KG_ROT) * 32);
        return;
    }
    const bf16 pdt = in.logdt[d];
    const uint32_t pla = reinterpret_cast<const uint32_t*>(in.logA)[d * KG_THREADS + tid], pai = reinterpret_cast<const uint32_t*>(in.Aim)[d * KG_THREADS + tid];
    const uint32_t pcr = reinterpret_cast<const uint32_t*>(in.Cre)[d * KG_THREADS + tid], pci = reinterpret_cast<const uint32_t*>(in.Cim)[d * KG_THREADS + tid];
    const bf16* pfq = tid < 30 ? in.wqkv + (size_t)(d * 30 + tid) * 64 : tid < 40 ? in.wo + (size_t)(d * 10 + tid - 30) * 64 : in.x + (size_t)(d * 32 + tid - 40) * 64;
#define KG_PF 0
    if (tid < (KG_PF == 3 ? 0 : KG_PF ? 40 : 72)) asm volatile("prefetch.global.L2 [%0];" ::"l"(pfq));
    asm volatile("st.global.v4.u32 [%0], {%1,%1,%1,%1};" ::"l"(in.halo + d * 148 + tid), "r"(~0u));
    if (tid < 52) asm volatile("st.global.v4.u32 [%0], {%1,%1,%1,%1};" ::"l"(in.halo + d * 148 + 96 + tid), "r"(~0u));
    else if (w16 == 2) {
        if (lane < 16) in.sum[blockIdx.x * 16 + lane] = make_uint4(0, 0, 0, 0);
        else if (lane < 20) reinterpret_cast<uint32_t*>(in.sum + 2048)[(blockIdx.x * 4 + lane - 16) * FSTR] = 0;
    }
    const uint32_t tw = smem_u32(tab) + warp * 12288;
    const int g = lane >> 2, t = lane & 3;
    const uint32_t sta = tw + lane * 128 + ((2 * (lane & 3) + ((lane >> 2) & 1)) << 4);
    const uint32_t lda = tw + t * 128 + ((g ^ (2 * t)) << 4);
    const uint32_t stb = tw + lane * 8, ldb = tw + g * 512 + (g & 3) * 32 + t * 8;
    auto sts4 = [&](int e, int off, uint32_t a, uint32_t b, uint32_t c, uint32_t dd) {
        asm volatile("st.shared.v4.u32 [%0], {%1,%2,%3,%4};" ::"r"((sta ^ (e << 4)) + off), "r"(a), "r"(b), "r"(c), "r"(dd) : "memory");
    };
    auto lds4 = [&](int sp, int off, uint32_t* r) {
        asm volatile("ld.shared.v4.u32 {%0,%1,%2,%3}, [%4];" : "=r"(r[0]), "=r"(r[1]), "=r"(r[2]), "=r"(r[3]) : "r"((lda ^ ((sp & 1) << 4)) + sp * 512 + off) : "memory");
    };
    const float dt = rbf(expf(bf2f(pdt)));
    float2 C[2], y1[2], z8[2], y128[2];
    float cmax = 0.f;
#pragma unroll
    for (int m = 0; m < 2; m++) {
        const float wr2 = -rbf(expf(__uint_as_float(m ? pla & 0xffff0000u : pla << 16))) * dt * 1.4426950408889634f;
        const float wi = __uint_as_float(m ? pai & 0xffff0000u : pai << 16) * dt;
        C[m] = make_float2(__uint_as_float(m ? pcr & 0xffff0000u : pcr << 16) * dt, -__uint_as_float(m ? pci & 0xffff0000u : pci << 16) * dt);
        cmax = fmaxf(cmax, fmaxf(fabsf(C[m].x), fabsf(C[m].y)));
        y1[m] = cexp_at(wr2, -wi, 1.f); z8[m] = cexp_at(wr2, wi, 8.f); y128[m] = cexp_at(wr2, -wi, 128.f);
    }
    const int ex = min(max((int)(__reduce_max_sync(~0u, __float_as_uint(cmax)) >> 23), 20), 240);
    const float scale = __uint_as_float((uint32_t)(127 + 10 + 127 - ex) << 23), unscale = 2.0f * __uint_as_float((uint32_t)(ex - 10) << 23);
    TSTAMPK(4, 64);
    if (KG_PF >= 2 && tid >= 40 && tid < 72) asm volatile("prefetch.global.L2 [%0];" ::"l"(pfq));
    float k2048 = 0.f;
    float acc[5][4];
#pragma unroll
    for (int j = 0; j < 5; j++)
#pragma unroll
        for (int k = 0; k < 4; k++) acc[j][k] = 0.f;
    uint32_t af[8][4];
    {
        float2 h0[2], h1[2], g0[2], g1[2], g2[2], g2b[2], g3[2], g4[2], y2[2], y4[2];
#pragma unroll
        for (int m = 0; m < 2; m++) {
            h0[m] = make_float2(1.f, 0.f); h1[m] = csqr(csqr(csqr(z8[m])));
            g0[m] = make_float2(C[m].x * scale, C[m].y * scale);
            g1[m] = cmul(g0[m], y128[m]);
            const float2 y256 = csqr(y128[m]), y512 = csqr(y256);
            g2b[m] = g2[m] = cmul(g0[m], y256); g3[m] = cmul(g0[m], y512); g4[m] = cmul(g3[m], y512);
            y2[m] = csqr(y1[m]); y4[m] = csqr(y2[m]);
            const float2 y1024 = csqr(y512);
            k2048 += fmaf(g4[m].x, y1024.x, -g4[m].y * y1024.y);
        }
#pragma unroll
        for (int e = 0; e < 8; e++) {
            sts4(e, 0, packh(h0[0]), packh(h1[0]), packh(h0[1]), packh(h1[1]));
            sts4(e, 4096, packh(g0[0]), packh(g0[1]), packh(g1[0]), packh(g1[1]));
#pragma unroll
            for (int m = 0; m < 2; m++)
                if (e < 7) { h0[m] = e ? cmul(h0[m], z8[m]) : z8[m]; h1[m] = cmul(h1[m], z8[m]); g0[m] = cmul(g0[m], y1[m]); g1[m] = cmul(g1[m], y1[m]); }
            if (e < 5) k2048 += __shfl_xor_sync(~0u, k2048, 1 << e);
        }
        if (KG_PF == 1 && tid >= 40 && tid < 72) asm volatile("prefetch.global.L2 [%0];" ::"l"(pfq));
        __syncwarp();
#pragma unroll
        for (int e = 0; e < 8; e++) {
            uint32_t b[4];
            lds4(e, 0, af[e]); lds4(e, 4096, b);
            sts4(e, 8192, packh(g2[0]), packh(g2[1]), packh((e & 1) ? cmul(g3[0], y4[0]) : g3[0]), packh((e & 1) ? cmul(g3[1], y4[1]) : g3[1]));
            asm volatile("st.shared.v2.u32 [%0], {%1,%2};" ::"r"((stb ^ ((e & 3) << 5)) + e * 512), "r"(packh(g4[0])), "r"(packh(g4[1])) : "memory");
#pragma unroll
            for (int m = 0; m < 2; m++)
                if (e < 7) {
                    g2[m] = e == 3 ? cmul(g2b[m], y128[m]) : cmul(g2[m], y2[m]);
                    if (e & 1) g3[m] = cmul(g3[m], y128[m]);
                    g4[m] = cmul(g4[m], y128[m]);
                }
            mma_f16(acc[0], af[e][0], af[e][1], af[e][2], af[e][3], b[0], b[1]);
            mma_f16(acc[1], af[e][0], af[e][1], af[e][2], af[e][3], b[2], b[3]);
        }
    }
    TSTAMPK(6, 64);
    __syncwarp();
#pragma unroll
    for (int sp = 0; sp < 8; sp++) {
        uint32_t c[4], e0, e1;
        lds4(sp, 8192, c);
        asm volatile("ld.shared.v2.u32 {%0,%1}, [%2];" : "=r"(e0), "=r"(e1) : "r"(ldb ^ (sp << 5)) : "memory");
        mma_f16(acc[2], af[sp][0], af[sp][1], af[sp][2], af[sp][3], c[0], c[1]);
        mma_f16(acc[3], af[sp][0], af[sp][1], af[sp][2], af[sp][3], c[2], c[3]);
        mma_f16(acc[4], af[sp][0], af[sp][1], af[sp][2], af[sp][3], e0, e1);
    }
    {
        float* Pp = reinterpret_cast<float*>(tab + warp * 768);
        auto sw = [](int i) { return i ^ ((i >> 2) & 24); };
#pragma unroll
        for (int h = 0; h < 2; h++) {
            const int b = g + 8 * h;
            *reinterpret_cast<float2*>(Pp + sw(8 * b + 2 * t)) = make_float2(acc[0][2 * h] * unscale, acc[0][2 * h + 1] * unscale);
            *reinterpret_cast<float2*>(Pp + 128 + sw(8 * b + 2 * t)) = make_float2(acc[1][2 * h] * unscale, acc[1][2 * h + 1] * unscale);
            *reinterpret_cast<float2*>(Pp + 256 + sw(4 * b + 2 * (t & 1) + 64 * (t >> 1))) = make_float2(acc[2][2 * h] * unscale, acc[2][2 * h + 1] * unscale);
            *reinterpret_cast<float2*>(Pp + 384 + sw(2 * b + 32 * t)) = make_float2(acc[3][2 * h] * unscale, acc[3][2 * h + 1] * unscale);
            Pp[512 + sw(b + 32 * t)] = acc[4][2 * h] * unscale;
            Pp[512 + sw(b + 32 * t + 16)] = acc[4][2 * h + 1] * unscale;
        }
        if (lane == 0) Pp[640] = k2048 * unscale;
    }
    TSTAMPK(7, 64);
    asm volatile("bar.sync %0, 128;" ::"r"(grp + 1) : "memory");
    TSTAMPK(9, 64);
    const float* Kp = reinterpret_cast<const float*>(tab);
    auto ksum = [&](int i) -> float { return (Kp[i] + Kp[3072 + i]) + Kp[6144 + i]; };
    auto ksum4 = [&](int q) -> float4 {
        q ^= (q >> 2) & 6;
        const float4 a = reinterpret_cast<const float4*>(Kp)[q], b = reinterpret_cast<const float4*>(Kp)[768 + q], c = reinterpret_cast<const float4*>(Kp)[1536 + q];
        return make_float4((a.x + b.x) + c.x, (a.y + b.y) + c.y, (a.z + b.z) + c.z, (a.w + b.w) + c.w);
    };
    {
        uint2* E4 = reinterpret_cast<uint2*>(in.tap + d * 128);
        float4 v = ksum4(tid), u = ksum4(96 + min(tid, 64));
        const float cor = rbf(ksum(tid == 95 ? 384 : 512));
        if (tid == 95) v.w -= cor;
        if (tid == 31) u.w -= cor;
        const uint32_t lo = pack2(v.x, v.y), hi = pack2(v.z, v.w);
        if (tid < 64) {
            E4[6 + tid] = make_uint2(lo, hi);
            E4[(tid < 32 ? 159 : 209 - 32) + tid] = make_uint2(pack2(u.x, u.y), pack2(u.z, u.w));
        } else {
            const uint32_t nx = __shfl_down_sync(~0u, lo, 1);
            in.tap[d * 128 + 35 + tid - 64] = make_uint4(__byte_perm(lo, 0, 0x1010), __byte_perm(lo, hi, 0x5432), __byte_perm(hi, 0, 0x1010), __byte_perm(hi, tid == 95 ? 0u : nx, 0x5432));
            if (tid == 64) E4[241] = make_uint2(pack2(u.x, 0.f), 0u);
        }
    }
    TSTAMPK(10, 64);
    if (warp < (blockIdx.x < 112 ? 2 : 1)) {
        const uint32_t sb = smem_u32(tabs);
        mbar_wait(sb + KG_BAR + 16 * warp, 0); mbar_wait(sb + KG_BAR + 16 * warp + 8, 0);
        uint32_t w[4][4];
        float cs[4] = {0.f, 0.f, 0.f, 0.f};
#pragma unroll
        for (int a = 0; a < 4; a++)
            ldsm_x4_t(w[a], sb + KG_BUF + warp * 10240 + grp * 1024 + ((lane >> 4) * 8 + (lane & 7)) * 32 + ((((lane >> 3) ^ (lane >> 2)) & 1) << 4) + (a >> 1) * 5120 + (a & 1) * 512);
#pragma unroll
        for (int a = 0; a < 4; a++) mma_bf16(cs, w[a][0], w[a][1], w[a][2], w[a][3], 0x3f803f80u, 0x3f803f80u);
        if (t < 2) in.csp[(blockIdx.x + 128 * warp) * 80 + grp * 16 + g + 8 * t] = t ? cs[2] : cs[0];
    }
    SPAN(0, 3);
}

#define CV_MODE 0
#define CV_LD __ldcg
#define CV_LDX __ldcg
#define CV_SLEEP 100
constexpr int CV_CPB = 5;
constexpr int CV_THREADS = 512;
constexpr int UPADF = 128;
constexpr int ULEN = UPADF + SEQ + 80;
constexpr int XLEN = SEQ + 16;
constexpr int BX_5 = 0, BX_3 = 3264, BX_9 = 6528, BX_7 = 8960, BX_LEN = 11392;
constexpr int CV_SM_T = 0;
constexpr int CV_SM_B = CV_CPB * TAPB;
constexpr int CV_SM_U = CV_SM_B + CV_CPB * BX_LEN;
constexpr int CV_SM_X = CV_SM_U + CV_CPB * ULEN * 2;
constexpr int CV_SM_Y = CV_SM_X + CV_CPB * XLEN * 2;
constexpr int CV_SM_P = CV_SM_Y + CV_CPB * XLEN * 2;
constexpr int CV_SM_CNT = CV_SM_P + 6 * 4096;
constexpr int CV_SM_O = (CV_SM_CNT + 128 + 127) & ~127;
constexpr int CV_SMEM = CV_SM_O + 20480;
static_assert(CV_SM_B % 128 == 0 && CV_SM_CNT % 16 == 0, "layout");

__device__ __forceinline__ uint32_t sub2(uint32_t x, uint32_t m) {
    const __nv_bfloat162 d = __hsub2(*reinterpret_cast<const __nv_bfloat162*>(&x), *reinterpret_cast<const __nv_bfloat162*>(&m));
    return *reinterpret_cast<const uint32_t*>(&d);
}
__device__ __forceinline__ uint32_t add2(uint32_t x, uint32_t y) {
    const __nv_bfloat162 d = __hadd2_rn(*reinterpret_cast<const __nv_bfloat162*>(&x), *reinterpret_cast<const __nv_bfloat162*>(&y));
    return *reinterpret_cast<const uint32_t*>(&d);
}
__device__ __forceinline__ void cp_async16(uint32_t dst, const void* src) {
    asm volatile("cp.async.cg.shared.global [%0], [%1], 16;" ::"r"(dst), "l"(src));
}
__device__ __forceinline__ void cp_async_wait_all() { asm volatile("cp.async.wait_all;" ::: "memory"); }

template <bool FULL>
__device__ __forceinline__ void direct_pass(float (&acc)[8][4], uint32_t ub, uint32_t o0, uint32_t o1, const uint2* __restrict__ Tp, bool first_half) {
    uint32_t sw[8][8];
#pragma unroll
    for (int j = 0; j < 8; j++) { ldsm_x4(&sw[j][0], ub + o0 + j * 256); ldsm_x4(&sw[j][4], ub + o1 + j * 256); }
#pragma unroll
    for (int M = 0; M < 4; M++) {
#pragma unroll
        for (int i = 0; i < 4; i++) {
            const uint2 hi = Tp[128 * M + 16 * i], lo = Tp[128 * M + 16 * i - 8];
#pragma unroll
            for (int j = FULL ? 0 : M; j < 8; j++) mma_bf16(acc[j], hi.x, hi.y, lo.x, lo.y, sw[(j - M) & 7][2 * i], sw[(j - M) & 7][2 * i + 1]);
        }
        if (FULL) {
            ldsm_x4(&sw[7 - M][0], ub + o0 - (M + 1) * 256);
            if (M < 3) ldsm_x4(&sw[7 - M][4], ub + o1 - (M + 1) * 256);
        }
    }
    if (first_half) {
        const uint2 hi = Tp[512], lo = Tp[504];
#pragma unroll
        for (int j = FULL ? 0 : 4; j < 8; j++) mma_bf16(acc[j], hi.x, hi.y, lo.x, lo.y, sw[(j - 4) & 7][0], sw[(j - 4) & 7][1]);
    }
}
__device__ __forceinline__ uint32_t fin2(uint32_t y, uint32_t u, uint32_t dk) {
    typedef __nv_bfloat162 b2;
    const b2 r = __hadd2_rn(*reinterpret_cast<const b2*>(&y), __hmul2_rn(*reinterpret_cast<const b2*>(&u), *reinterpret_cast<const b2*>(&dk)));
    return *reinterpret_cast<const uint32_t*>(&r);
}
__global__ void __launch_bounds__(CV_THREADS, 1) conv_kernel(const bf16* __restrict__ Dskip, int layer, const uint4* __restrict__ piv, const float4* __restrict__ sum, const bf16* __restrict__ x1T,
                                                             bf16* __restrict__ dst, const uint4* __restrict__ tap, bf16* __restrict__ yT, const __grid_constant__ CUtensorMap tmOut) {
    extern __shared__ __align__(128) unsigned char sm[];
    SPAN(3 + 4 * layer, 0);
    bf16* Us = reinterpret_cast<bf16*>(sm + CV_SM_U);
    bf16* Xs = reinterpret_cast<bf16*>(sm + CV_SM_X);
    bf16* Ys = reinterpret_cast<bf16*>(sm + CV_SM_Y);
    const int tid = threadIdx.x, lane = tid & 31, warp = __shfl_sync(~0u, tid >> 5, 0);
    const int d0 = blockIdx.x * CV_CPB, tile = blockIdx.x; (void)tile;
    const int g = lane >> 2, ti = lane & 3;
    const int e = g - 2 * ti;
    uint32_t lds_off[4];
    uint32_t off2, off3, offc;
    {
        const int mat = lane >> 3, r = lane & 7;
#pragma unroll
        for (int pr = 0; pr < 4; pr++) {
            const int iw = 2 * pr + (mat >> 1), half = mat & 1;
            const int chunk = (UPADF - 16 * iw + 16 * r + 8 * half) >> 3;
            lds_off[pr] = (uint32_t)((chunk ^ ((chunk >> 3) & 1)) * 16);
        }
        const int j2 = 13 + r + 8 * (mat >> 1), j3 = j2 + 2, i0 = 8 * (mat & 1);
        off2 = (j2 & 1) ? BX_3 + (4 * j2 + i0 + 84) * 2 : BX_5 + (4 * j2 + i0 + 80) * 2;
        off3 = ((j3 & 1) ? BX_7 : BX_9) + (8 * j3 + i0 + 136) * 2;
        const int cc = (UPADF + 16 * (r + (mat >> 1)) + i0) >> 3;
        offc = (uint32_t)((cc ^ ((cc >> 3) & 1)) * 16);
    }
#define CV_WX 0
    const int wv = warp ^ CV_WX;
    const uint32_t rtab = wv < 8 ? (wv < 4 ? 0x0B090200u : 0x0C0A0301u) : (wv < 12 ? 0x13111008u : 0x1412241Cu);
    const int rl = (rtab >> (8 * (warp & 3))) & 0xff, type = rl >> 3, c = rl & 7;
    const int H = (type == 1 || type == 2) ? 1 : 0, T0 = 8 * H;
    uint32_t toff = CV_SM_T + c * TAPB + (TPAD + e) * 8;
    uint32_t ubase = smem_u32(Us + c * ULEN);
    const uint32_t bbase = smem_u32(sm + CV_SM_B + c * BX_LEN);
    uint32_t rd0, rd1;
    {
        const uint32_t rstart = wv < 8 ? (wv < 4 ? 0x02000000u : 0x06040000u) : (wv < 12 ? 0x0C0B0A08u : 0x1E1D150Fu);
        const uint32_t rcount = wv < 8 ? 0x02020000u : (wv < 12 ? 0x03010102u : 0x01010806u);
        rd0 = (rstart >> (8 * (warp & 3))) & 0xff; rd1 = rd0 + ((rcount >> (8 * (warp & 3))) & 0xff);
    }
    asm volatile("" : "+r"(lds_off[0]), "+r"(lds_off[1]), "+r"(lds_off[2]), "+r"(lds_off[3]), "+r"(ubase), "+r"(toff), "+r"(rd0), "+r"(rd1));
    const uint2* Tc = reinterpret_cast<const uint2*>(sm + toff);
    TSTAMP1X(9, 256);
    unsigned short dskr;
    asm volatile("ld.global.nc.u16 %0, [%1];" : "=h"(dskr) : "l"(Dskip + d0 + min(lane, CV_CPB - 1)));
    if (tid >= 256) {
        const int t2 = tid - 256;
        if (t2 == 0) {
            mbar_init(smem_u32(sm + CV_SM_CNT) + 104, 1);
            asm volatile("fence.mbarrier_init.release.cluster;" ::: "memory");
            mbar_expect_tx(smem_u32(sm + CV_SM_CNT) + 104, CV_CPB * 2048);
            bulk_load(smem_u32(sm + CV_SM_O), tap + d0 * 128, CV_CPB * 2048, smem_u32(sm + CV_SM_CNT) + 104);
        } else if (lane == 0) {
            mbar_init(smem_u32(sm + CV_SM_CNT) + 16 * (warp - 9), warp == 15 ? 16 : 1);
            if (warp < 15) mbar_init(smem_u32(sm + CV_SM_CNT) + 16 * (warp - 9) + 8, 1);
            else if (layer) prefetch_tmap(&tmOut);
        }
        if (t2 < 149) {
            const int k = t2;
            const int off = k < 18 ? BX_5 + 8 * k : k < 37 ? BX_3 + 8 * (k - 18) : k < 69 ? BX_9 + 8 * (k - 37) : k < 101 ? BX_7 + 8 * (k - 69)
                          : k < 133 ? 8 * (k - 101) : (UPADF + SEQ) * 2 + 8 * (k - 133);
#pragma unroll
            for (int c = 0; c < CV_CPB; c++) *reinterpret_cast<uint2*>(sm + (k < 101 ? CV_SM_B + c * BX_LEN : CV_SM_U + c * ULEN * 2) + off) = make_uint2(0, 0);
        }
        asm volatile("bar.sync 1, 256;" ::: "memory");
        TSTAMP1X(10, 256);
        mbar_wait(smem_u32(sm + CV_SM_CNT) + 104, 0);
        TSTAMP1X(11, 256);
        {
            const int rx = (t2 & 15) < 4 ? t2 & 15 : 256 + (t2 & 15), cx = min(t2 >> 4, 4);
            uint32_t w[CV_CPB + 1][4];
#pragma unroll
            for (int c = 0; c <= CV_CPB; c++) {
                const uint32_t* E2 = reinterpret_cast<const uint32_t*>(sm + CV_SM_O) + (c < CV_CPB ? 512 * c + t2 + 7 : 512 * cx + rx + 3);
                w[c][0] = E2[0]; w[c][1] = E2[1]; w[c][2] = E2[4]; w[c][3] = E2[5];
            }
#pragma unroll
            for (int c = 0; c <= CV_CPB; c++)
                *reinterpret_cast<uint4*>(sm + CV_SM_T + (c < CV_CPB ? c * TAPB + (t2 + 4) * 16 : cx * TAPB + rx * 16)) =
                    make_uint4(__byte_perm(w[c][1], w[c][0], 0x7610), __byte_perm(w[c][3], w[c][2], 0x7610), __byte_perm(w[c][1], 0, 0x1032), __byte_perm(w[c][3], 0, 0x1032));
        }
        asm volatile("bar.arrive 2, 512;" ::: "memory");
        if ((t2 & 127) < 120) {
            const int r = 272 + (t2 & 127), c0 = t2 >> 7;
            const bool cc = r >= 368;
            const uint32_t* E2 = reinterpret_cast<const uint32_t*>(sm + CV_SM_O) + 512 * c0 + (r < 320 ? 301 + 2 * (r - 272) : cc ? 417 : 401 + 2 * (r - 320));
            const uint32_t* E3 = E2 + (cc ? 0 : 1);
            const uint32_t s0 = !cc ? 0x7610u : r == 382 ? 0x1044u : 0x4444u, s1 = !cc ? 0x7610u : r == 378 ? 0x1044u : 0x4444u;
            const uint32_t s2 = !cc ? 0x1032u : r == 381 ? 0x4410u : 0x4444u, s3 = !cc ? 0x1032u : r == 377 ? 0x4410u : 0x4444u;
            uint32_t w[3][4];
#pragma unroll
            for (int c = 0; c < 3; c++) { const int o = c < 2 ? 1024 * c : 2048 - 512 * c0; w[c][0] = E2[o]; w[c][1] = E2[o + 1]; w[c][2] = E3[o]; w[c][3] = E3[o + 1]; }
#pragma unroll
            for (int c = 0; c < 3; c++) {
                const uint32_t a = __byte_perm(w[c][3], w[c][2], s1), b = __byte_perm(w[c][1], w[c][0], s2);
                *reinterpret_cast<uint4*>(sm + CV_SM_T + (c < 2 ? 2 * c + c0 : 4) * TAPB + r * 16) =
                    make_uint4(__byte_perm(w[c][1], w[c][0], s0), cc ? a : b, cc ? b : a, __byte_perm(w[c][3], w[c][2], s3));
            }
        }
        TSTAMP1X(12, 256);
        if (layer == 0) {
#pragma unroll
            for (int c = 0; c < CV_CPB; c++) reinterpret_cast<uint4*>(yT + (size_t)(d0 + c) * XCP)[t2] = make_uint4(~0u, ~0u, ~0u, ~0u);
        }
        pdl_sync();
        if (layer && blockIdx.x == 0 && t2 == 0) g_epoch = ld_epoch();
        __syncwarp();
        asm volatile("bar.sync 3, 512;" ::: "memory");
    } else {
        const uint4* ppv = piv + tid;
        const float4* psv = sum + tid;
        const uint2* pxv = reinterpret_cast<const uint2*>(x1T + (size_t)d0 * XCP) + (tid >> 4) * 32 + (tid & 15);
        asm volatile("st.shared.u64 [%0], %1;" ::"r"(smem_u32(Ys) + tid * 8), "l"((uint64_t)ppv ^ (uint64_t)psv ^ (uint64_t)pxv) : "memory");
        pdl_sync();
        SPAN(3 + 4 * layer, 1);
        TSTAMP(0);
        if (threadIdx.x == 0) { GSTAMP(g_tim, 15); }
        float4 sv[4];
#pragma unroll
        for (int k = 0; k < 4; k++) sv[k] = CV_LD(psv + 256 * k);
        const uint4 pv = CV_LD(ppv);
        uint2 xe[CV_CPB], xo[CV_CPB];
#pragma unroll
        for (int c = 0; c < CV_CPB; c++) { xe[c] = CV_LDX(pxv + c * (XCP / 4)); xo[c] = CV_LDX(pxv + c * (XCP / 4) + 16); }
        uint32_t mw[4];
        float rs[8];
#pragma unroll
        for (int k = 0; k < 4; k++) {
            const uint32_t pw = k == 0 ? pv.x : k == 1 ? pv.y : k == 2 ? pv.z : pv.w;
            const float d0_ = sv[k].x * (1.0f / DM), d1_ = sv[k].z * (1.0f / DM);
            mw[k] = pack2(__uint_as_float(pw << 16) + d0_, __uint_as_float(pw & 0xffff0000u) + d1_);
            const uint32_t vr = pack2(fmaxf(fmaf(-d0_, d0_, sv[k].y * (1.0f / DM)), 0.f), fmaxf(fmaf(-d1_, d1_, sv[k].w * (1.0f / DM)), 0.f));
            const uint32_t ve = pack2(__uint_as_float(vr << 16) + 1e-5f, __uint_as_float(vr & 0xffff0000u) + 1e-5f);
            const uint32_t sd = pack2(sqrt_apx(__uint_as_float(ve << 16)), sqrt_apx(__uint_as_float(ve & 0xffff0000u)));
            rs[2 * k] = rcp_apx(__uint_as_float(sd << 16)); rs[2 * k + 1] = rcp_apx(__uint_as_float(sd & 0xffff0000u));
        }
        if (rs[0] != 123.f) TSTAMP(13);
        const int ch = tid + UPADF / 8, pch = ch ^ ((ch >> 3) & 1);
#pragma unroll
        for (int c = 0; c < CV_CPB; c++) {
            *reinterpret_cast<uint4*>(Xs + c * XLEN + tid * 8) = make_uint4(xe[c].x, xe[c].y, xo[c].x, xo[c].y);
            const uint32_t e0 = sub2(xe[c].x, mw[0]), e1 = sub2(xe[c].y, mw[1]), o0 = sub2(xo[c].x, mw[2]), o1 = sub2(xo[c].y, mw[3]);
            *reinterpret_cast<uint4*>(Us + c * ULEN + pch * 8) =
                make_uint4(pack2(__uint_as_float(e0 << 16) * rs[0], __uint_as_float(o0 << 16) * rs[4]), pack2(__uint_as_float(e0 & 0xffff0000u) * rs[1], __uint_as_float(o0 & 0xffff0000u) * rs[5]),
                           pack2(__uint_as_float(e1 << 16) * rs[2], __uint_as_float(o1 << 16) * rs[6]), pack2(__uint_as_float(e1 & 0xffff0000u) * rs[3], __uint_as_float(o1 & 0xffff0000u) * rs[7]));
        }
        asm volatile("bar.arrive 3, 512;" ::: "memory");
        asm volatile("bar.sync 2, 512;" ::: "memory");
    }
    TSTAMP(1);
#pragma unroll 1
    for (int rd = rd0; rd < (int)rd1; rd++) {
        const int i = 32 * rd + lane;
        if (i < CV_CPB * 193) {
            const int c = i / 193, chunk = i - c * 193 - 1, ch = chunk + UPADF / 8;
            const bf16* uc = Us + c * ULEN;
            const uint4 o = *reinterpret_cast<const uint4*>(uc + (ch ^ ((ch >> 3) & 1)) * 8);
            const uint2 lo = *reinterpret_cast<const uint2*>(uc + ((ch - 1) ^ (((ch - 1) >> 3) & 1)) * 8 + 4);
            const uint2 hi = *reinterpret_cast<const uint2*>(uc + ((ch + 1) ^ (((ch + 1) >> 3) & 1)) * 8);
            const uint32_t w[8] = {lo.x, lo.y, o.x, o.y, o.z, o.w, hi.x, hi.y};
            float v[16], b[8];
#pragma unroll
            for (int k = 0; k < 8; k++) { v[2 * k] = __uint_as_float(w[k] << 16); v[2 * k + 1] = __uint_as_float(w[k] & 0xffff0000u); }
            unsigned char* bx = sm + CV_SM_B + c * BX_LEN + chunk * 16;
#pragma unroll
            for (int k = 0; k < 8; k++) b[k] = v[k + 4] + (v[k + 3] + v[k + 5]);
            *reinterpret_cast<uint2*>(bx + BX_3 + 168) = make_uint2(pack2(b[0], b[1]), pack2(b[2], b[3]));
            *reinterpret_cast<uint2*>(bx + BX_3 + 176) = make_uint2(pack2(b[4], b[5]), pack2(b[6], b[7]));
#pragma unroll
            for (int k = 0; k < 8; k++) b[k] += v[k + 2] + v[k + 6];
            *reinterpret_cast<uint4*>(bx + BX_5 + 160) = make_uint4(pack2(b[0], b[1]), pack2(b[2], b[3]), pack2(b[4], b[5]), pack2(b[6], b[7]));
            if (chunk < 128) {
#pragma unroll
                for (int k = 0; k < 8; k++) b[k] += v[k + 1] + v[k + 7];
                *reinterpret_cast<uint4*>(bx + BX_7 + 272) = make_uint4(pack2(b[0], b[1]), pack2(b[2], b[3]), pack2(b[4], b[5]), pack2(b[6], b[7]));
#pragma unroll
                for (int k = 0; k < 8; k++) b[k] += v[k] + v[k + 8];
                *reinterpret_cast<uint4*>(bx + BX_9 + 272) = make_uint4(pack2(b[0], b[1]), pack2(b[2], b[3]), pack2(b[4], b[5]), pack2(b[6], b[7]));
            }
        }
    }
    __syncwarp();
    if (lane == 0) mbar_arrive(smem_u32(sm + CV_SM_CNT) + 96);
    TSTAMP(2);
    {
        float acc[8][4];
#pragma unroll
        for (int j = 0; j < 8; j++)
#pragma unroll
            for (int k = 0; k < 4; k++) acc[j][k] = 0.f;
#pragma unroll 1
        for (int pass = (type == 2 || type == 4) ? 1 : 0; pass < ((type == 1 || type == 3) ? 1 : 2); pass++) {
            const uint32_t o0 = pass ? lds_off[2] : lds_off[0], o1 = pass ? lds_off[3] : lds_off[1];
            if (H) direct_pass<true>(acc, ubase + T0 * 256, o0, o1, Tc + 64 * pass, pass == 0);
            else direct_pass<false>(acc, ubase, o0, o1, Tc + 64 * pass, pass == 0);
        }
        TSTAMP(6);
        mbar_wait(smem_u32(sm + CV_SM_CNT) + 96, 0);
        if (type != 1 && type != 4) {
            const uint32_t* w2 = reinterpret_cast<const uint32_t*>(sm + CV_SM_T + c * TAPB + TAP_W2) + (115 - 96) + 4 * g - 2 * ti;
            uint32_t f[10][2];
#pragma unroll
            for (int k = 0; k < 10; k++) { f[k][0] = w2[16 * k]; f[k][1] = w2[16 * k - 8]; }
            const uint32_t ab = bbase + off2 + (2 * T0 + 6) * 128;
            const int kmax = H ? 23 : 8;
            uint32_t a[3][4];
            ldsm_x4_t(a[0], ab);
            ldsm_x4_t(a[1], ab - 128);
#pragma unroll
            for (int kp = 0; kp < 24; kp++) {
                if (kp > kmax) break;
                if (kp < 22) ldsm_x4_t(a[(kp + 2) % 3], ab - min(kp + 2, kmax) * 128);
#pragma unroll
                for (int j = 0; j < 8; j++) {
                    const int ee = 2 * j - 14 + kp;
                    if (ee >= 0 && ee <= 9) mma_bf16(acc[j], a[kp % 3][0], a[kp % 3][1], a[kp % 3][2], a[kp % 3][3], f[ee][0], f[ee][1]);
                }
            }
        }
        TSTAMP(7);
        if (type != 2 && type != 4) {
            const uint32_t* w3 = reinterpret_cast<const uint32_t*>(sm + CV_SM_T + c * TAPB + TAP_W3) + (129 - 96) + 2 * (g - ti);
            uint32_t f[9][2];
#pragma unroll
            for (int k = 0; k < 9; k++) { f[k][0] = w3[16 * k]; f[k][1] = w3[16 * k - 8]; }
            const uint32_t ab = bbase + off3 + (T0 - 2) * 256;
            uint32_t a[3][4];
            ldsm_x4_t(a[0], ab);
            ldsm_x4_t(a[1], ab - H * 256);
#pragma unroll
            for (int kp = 0; kp < 9; kp++) {
                if (kp > T0) break;
                if (kp < 7) ldsm_x4_t(a[(kp + 2) % 3], ab - min(kp + 2, T0) * 256);
#pragma unroll
                for (int j = 0; j < 8; j++) {
                    const int dl = j - 7 + kp;
                    if (dl >= 0 && dl <= 8) mma_bf16(acc[j], a[kp % 3][0], a[kp % 3][1], a[kp % 3][2], a[kp % 3][3], f[dl][0], f[dl][1]);
                }
            }
            const uint2* Dc = reinterpret_cast<const uint2*>(sm + CV_SM_T + c * TAPB + TAP_C) + e;
            const uint2 h63 = Dc[16], h64 = Dc[32], l63 = Dc[8], l64 = Dc[24];
#pragma unroll
            for (int j = 0; j < 8; j++)
                if (j == 7 || H) {
                    uint32_t bq[4];
                    ldsm_x4(bq, ubase + offc + (T0 + j - 8) * 256);
                    mma_bf16(acc[j], h64.x, h64.y, l64.x, l64.y, bq[0], bq[1]);
                    mma_bf16(acc[j], h63.x, h63.y, l63.x, l63.y, bq[2], bq[3]);
                }
        }
        TSTAMP(8);
        int hh = (0x14 >> type) & 1;
        asm volatile("" : "+r"(hh));
        const bool hi_half = hh;
        if (type != 0) {
            const int pair = H ? c : 5;
            float4* give = reinterpret_cast<float4*>(sm + CV_SM_P + pair * 4096 + (hi_half ? 2048 : 0)) + lane;
            const float4* take = reinterpret_cast<const float4*>(sm + CV_SM_P + pair * 4096 + (hi_half ? 0 : 2048)) + lane;
            const uint32_t pb = smem_u32(sm + CV_SM_CNT) + pair * 16;
#pragma unroll
            for (int j = 0; j < 8; j++)
                asm volatile("{\n.reg .pred p;\nsetp.eq.s32 p, %5, %6;\n@p st.shared.v4.f32 [%0], {%1,%2,%3,%4};\n}"
                             ::"r"(smem_u32(give + 32 * (j & 3))), "f"(acc[j][0]), "f"(acc[j][1]), "f"(acc[j][2]), "f"(acc[j][3]), "r"(hh), "r"(j < 4 ? 1 : 0) : "memory");
            __syncwarp();
            if (lane == 0) mbar_arrive(pb + (hi_half ? 8 : 0));
            mbar_wait(pb + (hi_half ? 0 : 8), 0);
#pragma unroll
            for (int j = 0; j < 4; j++) {
                const float4 v = take[32 * j];
                acc[j][0] = (hi_half ? acc[j + 4][0] : acc[j][0]) + v.x; acc[j][1] = (hi_half ? acc[j + 4][1] : acc[j][1]) + v.y;
                acc[j][2] = (hi_half ? acc[j + 4][2] : acc[j][2]) + v.z; acc[j][3] = (hi_half ? acc[j + 4][3] : acc[j][3]) + v.w;
            }
        }
        const uint32_t dk = __shfl_sync(~0u, (uint32_t)dskr, c) * 0x10001u;
#pragma unroll 1
        for (int rnd = 0; rnd < (type == 0 ? 2 : 1); rnd++) {
            const int Q = 2 * H + (hi_half ? 1 : rnd);
            if (rnd) {
#pragma unroll
                for (int j = 0; j < 4; j++)
#pragma unroll
                    for (int k = 0; k < 4; k++) acc[j][k] = acc[j + 4][k];
            }
            const uint32_t ya = smem_u32(Ys + c * XLEN) + (128 * (4 * Q + (lane >> 4)) + 16 * (lane & 7) + 8 * ((lane >> 3) & 1)) * 2;
#pragma unroll
            for (int j = 0; j < 4; j += 2)
                asm volatile("stmatrix.sync.aligned.m8n8.x4.trans.shared.b16 [%0], {%1,%2,%3,%4};" ::"r"(ya + j * 256),
                             "r"(pack2(acc[j][0], acc[j][1])), "r"(pack2(acc[j][2], acc[j][3])),
                             "r"(pack2(acc[j + 1][0], acc[j + 1][1])), "r"(pack2(acc[j + 1][2], acc[j + 1][3])) : "memory");
            __syncwarp();
            uint4 yv[2], xv[2], uv[2];
#pragma unroll
            for (int k = 0; k < 2; k++) {
                const int t = 512 * Q + 256 * k + 8 * lane, cu = (t + UPADF) >> 3;
                yv[k] = *reinterpret_cast<const uint4*>(Ys + c * XLEN + t);
                xv[k] = *reinterpret_cast<const uint4*>(Xs + c * XLEN + t);
                uv[k] = *reinterpret_cast<const uint4*>(Us + c * ULEN + (cu ^ ((cu >> 3) & 1)) * 8);
            }
#pragma unroll
            for (int k = 0; k < 2; k++) {
                const uint32_t z0 = fin2(yv[k].x, uv[k].x, dk), z1 = fin2(yv[k].y, uv[k].y, dk), z2 = fin2(yv[k].z, uv[k].z, dk), z3 = fin2(yv[k].w, uv[k].w, dk);
                if (layer)
                    asm volatile("st.relaxed.gpu.global.v4.u32 [%0], {%1,%2,%3,%4};" ::"l"(dst + (size_t)(d0 + c) * XCP + 512 * Q + 256 * k + 8 * lane),
                                 "r"(add2(__byte_perm(xv[k].x, xv[k].z, 0x5410), z0)), "r"(add2(__byte_perm(xv[k].x, xv[k].z, 0x7632), z1)),
                                 "r"(add2(__byte_perm(xv[k].y, xv[k].w, 0x5410), z2)), "r"(add2(__byte_perm(xv[k].y, xv[k].w, 0x7632), z3)) : "memory");
                else {
                    uint2* dp = reinterpret_cast<uint2*>(dst + (size_t)(d0 + c) * XCP + 512 * Q + 256 * k) + (lane >> 4) * 32 + (lane & 15);
                    dp[0] = make_uint2(add2(xv[k].x, __byte_perm(z0, z1, 0x5410)), add2(xv[k].y, __byte_perm(z2, z3, 0x5410)));
                    dp[16] = make_uint2(add2(xv[k].z, __byte_perm(z0, z1, 0x7632)), add2(xv[k].w, __byte_perm(z2, z3, 0x7632)));
                }
            }
        }
        TSTAMP(4);
        if (layer == 1) {
            const int mb = blockIdx.x >> 3, cg = blockIdx.x & 7;
            const bf16* src = dst + (size_t)(cg * 80 + (tid >> 4)) * XCP + mb * 128 + (tid & 15) * 8;
            uint32_t v[3][4];
            __syncthreads();
            TSTAMP(5);
            uint32_t todo = warp < 8 ? 7 : 3;
#pragma unroll 1
            for (int it = 0; it < SPIN_MAX; it++) {
#pragma unroll
                for (int k = 0; k < 3; k++)
                    if (todo >> k & 1)
                        asm volatile("ld.relaxed.gpu.global.v4.u32 {%0,%1,%2,%3}, [%4];" : "=r"(v[k][0]), "=r"(v[k][1]), "=r"(v[k][2]), "=r"(v[k][3]) : "l"(src + k * (32 * XCP)) : "memory");
#pragma unroll
                for (int k = 0; k < 3; k++)
                    if ((todo >> k & 1) && v[k][0] != ~0u && v[k][1] != ~0u && v[k][2] != ~0u && v[k][3] != ~0u) {
                        *reinterpret_cast<uint4*>(sm + (32 * k + (tid >> 4)) * 272 + (tid & 15) * 16) = make_uint4(v[k][0], v[k][1], v[k][2], v[k][3]);
                        todo ^= 1u << k;
                    }
                if (!todo) break;
                __nanosleep(CV_SLEEP);
            }
            __syncthreads();
            uint32_t w[12];
#pragma unroll
            for (int k = 0; k < 3; k++) ldsm_x4(&w[4 * k], smem_u32(sm) + min(32 * k + lane, 79) * 272 + warp * 16);
            const uint32_t ot = smem_u32(sm + CV_SM_O) + warp * 1280, oa = ot + (lane & 7) * 160 + (lane >> 3) * 16;
            stsm_x4_t(oa, w[0], w[1], w[2], w[3]);
            stsm_x4_t(oa + 64, w[4], w[5], w[6], w[7]);
            asm volatile("stmatrix.sync.aligned.m8n8.x2.trans.shared.b16 [%0], {%1,%2};" ::"r"(oa + 128), "r"(w[8]), "r"(w[9]) : "memory");
            fence_async_smem();
            __syncwarp();
            if (lane == 0) tma_store_2d(&tmOut, cg * 80, mb * 128 + 8 * warp, ot);
        }
    }
    TSTAMP(3);
    GSTAMP(g_tim, 14);
    SPAN(3 + 4 * layer, 3);
}

__device__ __forceinline__ void wgmma_fence() { asm volatile("wgmma.fence.sync.aligned;" ::: "memory"); }
__device__ __forceinline__ void wgmma_commit() { asm volatile("wgmma.commit_group.sync.aligned;" ::: "memory"); }
template <int N> __device__ __forceinline__ void wgmma_wait() { asm volatile("wgmma.wait_group.sync.aligned %0;" ::"n"(N) : "memory"); }
__device__ __forceinline__ uint64_t make_desc(uint32_t addr, uint32_t lbo, uint32_t sbo, uint32_t mode) {
    return (uint64_t)((addr & 0x3FFFF) >> 4) | ((uint64_t)(lbo >> 4) << 16) | ((uint64_t)(sbo >> 4) << 32) | ((uint64_t)mode << 62);
}
template <int TA, int TB>
__device__ __forceinline__ void wgmma_n240(float (&d)[120], uint64_t da, uint64_t db, int acc) {
    asm volatile("{\n.reg .pred p;\nsetp.ne.b32 p, %124, 0;\nwgmma.mma_async.sync.aligned.m64n240k16.f32.bf16.bf16 {%0,%1,%2,%3,%4,%5,%6,%7,%8,%9,%10,%11,%12,%13,%14,%15,%16,%17,%18,%19,%20,%21,%22,%23,%24,%25,%26,%27,%28,%29,%30,%31,%32,%33,%34,%35,%36,%37,%38,%39,%40,%41,%42,%43,%44,%45,%46,%47,%48,%49,%50,%51,%52,%53,%54,%55,%56,%57,%58,%59,%60,%61,%62,%63,%64,%65,%66,%67,%68,%69,%70,%71,%72,%73,%74,%75,%76,%77,%78,%79,%80,%81,%82,%83,%84,%85,%86,%87,%88,%89,%90,%91,%92,%93,%94,%95,%96,%97,%98,%99,%100,%101,%102,%103,%104,%105,%106,%107,%108,%109,%110,%111,%112,%113,%114,%115,%116,%117,%118,%119}, %120, %121, p, 1, 1, %122, %123;\n}"
                 : "+f"(d[0]), "+f"(d[1]), "+f"(d[2]), "+f"(d[3]), "+f"(d[4]), "+f"(d[5]), "+f"(d[6]), "+f"(d[7]), "+f"(d[8]), "+f"(d[9]), "+f"(d[10]), "+f"(d[11]), "+f"(d[12]), "+f"(d[13]), "+f"(d[14]), "+f"(d[15]), "+f"(d[16]), "+f"(d[17]), "+f"(d[18]), "+f"(d[19]), "+f"(d[20]), "+f"(d[21]), "+f"(d[22]), "+f"(d[23]), "+f"(d[24]), "+f"(d[25]), "+f"(d[26]), "+f"(d[27]), "+f"(d[28]), "+f"(d[29]), "+f"(d[30]), "+f"(d[31]), "+f"(d[32]), "+f"(d[33]), "+f"(d[34]), "+f"(d[35]), "+f"(d[36]), "+f"(d[37]), "+f"(d[38]), "+f"(d[39]), "+f"(d[40]), "+f"(d[41]), "+f"(d[42]), "+f"(d[43]), "+f"(d[44]), "+f"(d[45]), "+f"(d[46]), "+f"(d[47]), "+f"(d[48]), "+f"(d[49]), "+f"(d[50]), "+f"(d[51]), "+f"(d[52]), "+f"(d[53]), "+f"(d[54]), "+f"(d[55]), "+f"(d[56]), "+f"(d[57]), "+f"(d[58]), "+f"(d[59]), "+f"(d[60]), "+f"(d[61]), "+f"(d[62]), "+f"(d[63]), "+f"(d[64]), "+f"(d[65]), "+f"(d[66]), "+f"(d[67]), "+f"(d[68]), "+f"(d[69]), "+f"(d[70]), "+f"(d[71]), "+f"(d[72]), "+f"(d[73]), "+f"(d[74]), "+f"(d[75]), "+f"(d[76]), "+f"(d[77]), "+f"(d[78]), "+f"(d[79]), "+f"(d[80]), "+f"(d[81]), "+f"(d[82]), "+f"(d[83]), "+f"(d[84]), "+f"(d[85]), "+f"(d[86]), "+f"(d[87]), "+f"(d[88]), "+f"(d[89]), "+f"(d[90]), "+f"(d[91]), "+f"(d[92]), "+f"(d[93]), "+f"(d[94]), "+f"(d[95]), "+f"(d[96]), "+f"(d[97]), "+f"(d[98]), "+f"(d[99]), "+f"(d[100]), "+f"(d[101]), "+f"(d[102]), "+f"(d[103]), "+f"(d[104]), "+f"(d[105]), "+f"(d[106]), "+f"(d[107]), "+f"(d[108]), "+f"(d[109]), "+f"(d[110]), "+f"(d[111]), "+f"(d[112]), "+f"(d[113]), "+f"(d[114]), "+f"(d[115]), "+f"(d[116]), "+f"(d[117]), "+f"(d[118]), "+f"(d[119])
                 : "l"(da), "l"(db), "n"(TA), "n"(TB), "r"(acc));
}

__device__ __forceinline__ void wgmma_n80(float (&d)[40], uint64_t da, uint64_t db, int acc) {
    asm volatile("{\n.reg .pred p;\nsetp.ne.b32 p, %42, 0;\nwgmma.mma_async.sync.aligned.m64n80k16.f32.bf16.bf16 {%0,%1,%2,%3,%4,%5,%6,%7,%8,%9,%10,%11,%12,%13,%14,%15,%16,%17,%18,%19,%20,%21,%22,%23,%24,%25,%26,%27,%28,%29,%30,%31,%32,%33,%34,%35,%36,%37,%38,%39}, %40, %41, p, 1, 1, 0, 1;\n}"
                 : "+f"(d[0]), "+f"(d[1]), "+f"(d[2]), "+f"(d[3]), "+f"(d[4]), "+f"(d[5]), "+f"(d[6]), "+f"(d[7]), "+f"(d[8]), "+f"(d[9]), "+f"(d[10]), "+f"(d[11]), "+f"(d[12]), "+f"(d[13]), "+f"(d[14]), "+f"(d[15]), "+f"(d[16]), "+f"(d[17]), "+f"(d[18]), "+f"(d[19]), "+f"(d[20]), "+f"(d[21]), "+f"(d[22]), "+f"(d[23]), "+f"(d[24]), "+f"(d[25]), "+f"(d[26]), "+f"(d[27]), "+f"(d[28]), "+f"(d[29]), "+f"(d[30]), "+f"(d[31]), "+f"(d[32]), "+f"(d[33]), "+f"(d[34]), "+f"(d[35]), "+f"(d[36]), "+f"(d[37]), "+f"(d[38]), "+f"(d[39])
                 : "l"(da), "l"(db), "r"(acc));
}

constexpr int A1_THREADS = 384;
constexpr int A1_NST = 4;
#define A1_SKEW 8
constexpr int A1_STAGE = 16384 + WQ_STAGE;
constexpr int A1_KVP = 336;
constexpr int A1_SM_KV = 2 * A1_STAGE;
constexpr int A1_SM_BAR = A1_NST * A1_STAGE;
constexpr int A1_SM_RS = A1_SM_BAR + 512;
constexpr int A1_SM_W0 = A1_SM_BAR + 3072, A1_SM_W3 = A1_SM_BAR - 3 * WOB, A1_SM_A1 = 2 * WOB, A1_SM_A0 = A1_SM_A1 + 61440;
constexpr int A1_SM_XA = A1_SM_W0 + 2 * WOB, A1_SM_XB = A1_SM_XA + 2048;
constexpr int A1_SMEM = A1_SM_W0 + 3 * WOB;
static_assert(A1_SM_W3 >= A1_SM_KV + 144 * A1_KVP && A1_SM_W3 % 512 == 0 && A1_SM_A1 % 1024 == 0 && A1_SM_A0 <= A1_SM_KV && A1_SM_A0 + 61440 <= A1_SM_W3 && A1_SMEM <= 232448, "layout");
__device__ __forceinline__ constexpr uint32_t wo_off(int h) { return h * WOB + (h < 3 ? A1_SM_W0 : h < 6 ? A1_SM_W3 - 3 * WOB : -6 * WOB); }
#define A1_FRED "red.relaxed.gpu.global.add.u32"
#define A1_FLD "ld.acquire.gpu.global.u32"
#define ST_SLEEP 20
#define ST_SLEEP0 300
#define WO_LATE bar_done
#define A1_P0 2
#define A1_PW (kb - 2)
#define A1_FSPIN SPIN_MAX
#define A1_FSLEEP 40
#define A1_WOAT 6

template <int L>
__device__ __forceinline__ void a1_mainloop(float (&acc)[120], uint32_t sbase, uint32_t bars, int wg, int tile) {
    constexpr int layer = L; (void)layer;
    const uint64_t da0 = L ? make_desc(sbase + wg * 8192, 8192, 1024, 1) : make_desc(sbase + wg * 8192, 16, 1024, 1), db0 = make_desc(sbase + 16384, 1024, 256, 3);
#pragma unroll 1
    for (int t = 0;; t++) {
        const int st = t % A1_NST;
        mbar_wait(bars + 8 * st, (t / A1_NST) & 1);
        if (t == A1_SKEW && wg == 0) mbar_wait(bars + 160, 0);
        TSTAMP3(1 + t);
        wgmma_fence();
#pragma unroll
        for (int kk = 0; kk < 4; kk++) wgmma_n240<L, 1>(acc, da0 + (uint32_t)(st * (A1_STAGE / 16) + kk * (L ? 128 : 2)), db0 + (uint32_t)(st * (A1_STAGE / 16) + (kk >> 1) * (WQ_STAGE / 32) + (kk & 1) * 32), kk ? 1 : t);
        wgmma_commit();
        if (t == 9) break;
        if (t == A1_SKEW - 1 && wg == 0) wgmma_wait<0>(); else wgmma_wait<1>();
        if (t > 0 && (threadIdx.x & 127) == 0) {
            if (t != A1_SKEW || wg) mbar_arrive(bars + 8 * (A1_NST + (t - 1) % A1_NST));
            if (t == A1_SKEW - 1 && wg == 0) mbar_arrive(bars + 8 * (A1_NST + t % A1_NST));
        }
    }
}

__global__ void __launch_bounds__(A1_THREADS, 1) a1_kernel(const int layer, const bf16* __restrict__ x0, const unsigned char* __restrict__ wq, const unsigned char* __restrict__ wo,
                                                           float2* __restrict__ rsum, uint4* __restrict__ of, const __grid_constant__ CUtensorMap tmX,
                                                           const __grid_constant__ CUtensorMap tmR, const __grid_constant__ CUtensorMap tmX1, const __grid_constant__ TileTab tab) {
    extern __shared__ __align__(1024) unsigned char stg[];
    const uint32_t sbase = smem_u32(stg);
    const uint32_t bars = sbase + A1_SM_BAR;
    const uint32_t bar_stat = bars + 64, bar_kv = bars + 72, bar_rd = bars + 168;
    const uint32_t bar_wo = bars + 208, bar_done = bars + 216, bar_pv = bars + 224, bar_kvf = bars + 232, bar_f2 = bars + 248, bar_e2 = bars + 384, que = bars + 448;
    const int tid = threadIdx.x;
    const int w = __shfl_sync(~0u, tid >> 5, 0), wg = w >> 2;
    uint32_t smid, ns;
    asm volatile("mov.u32 %0, %smid;" : "=r"(smid));
    asm volatile("mov.u32 %0, %nsmid;" : "=r"(ns));
    const auto te = tab.e[ns == tab.ns ? smid : 132 + blockIdx.x];
    const int tile = te.tile, mb = te.mb, hg = te.hg;
    float2* rst = reinterpret_cast<float2*>(stg + A1_SM_RS) + 8;
    auto issue_w = [&](int it) { bulk_load(sbase + (it % A1_NST) * A1_STAGE + 16384, wq + te.woff + it * WQ_STAGE, WQ_STAGE, bars + 8 * (it % A1_NST)); };
    auto issue_x = [&](int it, int kb) {
        asm volatile("cp.async.bulk.tensor.5d.shared::cluster.global.mbarrier::complete_tx::bytes [%0], [%1, {%3, %3, %3, %4, %5}], [%2];"
                     ::"r"(sbase + (it % A1_NST) * A1_STAGE), "l"(&tmX), "r"(bars + 8 * (it % A1_NST)), "r"(0), "r"(mb), "r"(kb) : "memory");
    };
    if (w == 8 && tile < 128) {
        const bool one = elect();
        if (one) {
#pragma unroll
            for (int i = 0; i < A1_NST; i++) mbar_init(bars + 8 * i, 1);
            asm volatile("fence.mbarrier_init.release.cluster;" ::: "memory");
        }
        __syncwarp();
        asm volatile("bar.arrive 0, 384;" ::: "memory");
        if (one) {
#define PW asm volatile("griddepcontrol.wait;" ::: "memory");
            if (layer) { issue_w(0); PW issue_x(0, te.kb0); issue_x(1, te.kb0 + 1); }
            else { issue_x(0, te.kb0); issue_x(1, te.kb0 + 1); PW issue_w(0); }
            issue_w(1);
#pragma unroll
            for (int i = 0; i < A1_NST; i++) mbar_expect_tx(bars + 8 * i, A1_STAGE);
            asm volatile("griddepcontrol.launch_dependents;" ::: "memory");
#pragma unroll
            for (int kb = 2; kb < A1_P0; kb++) { issue_x(kb, te.kb0 + kb); issue_w(kb); }
            DBGC(34); DBGV(33, smid); DBGV(40, t_entry); DBGV(30, t_a); DBGV(31, t_b); DBGV(32, t_c); DBGV(38, t_d); DBGV(39, t_e);
        }
    }
    if (tile >= 128) { sm_idle(layer); return; }
    if (wg == 2) {
        if (w != 8) {
            if (tid == 320) { prefetch_tmap(&tmX); prefetch_tmap(&tmR); prefetch_tmap(&tmX1); }
            asm volatile("bar.sync 0, 384;" ::: "memory");
        }
        if (w == 9) {
            asm volatile("bar.arrive 3, 64;" ::: "memory");
            if (layer == 0) pdl_sync();
            float4 a[2] = {};
#pragma unroll
            for (int k = 0; k < 10; k++)
#pragma unroll
                for (int h = 0; h < 2; h++) {
                    const int c4 = min(tid - 288 + 32 * h, 59);
                    const float4 v = __ldcg(reinterpret_cast<const float4*>(g_csp + k * 1920 + hg * 80) + c4 + (c4 / 20) * 140);
                    a[h].x += v.x; a[h].y += v.y; a[h].z += v.z; a[h].w += v.w;
                }
#pragma unroll
            for (int h = 0; h < 2; h++)
#pragma unroll
                for (int k = 0; k < 4; k++) {
                    const float c = 0.5f * (k == 0 ? a[h].x : k == 1 ? a[h].y : k == 2 ? a[h].z : a[h].w), c1 = c - rbf(c), c2 = c1 - rbf(c1);
                    *reinterpret_cast<uint4*>(stg + A1_SM_XB + (4 * min(tid - 288 + 32 * h, 59) + k) * 16) = make_uint4(pack2(c, c1), pack2(c2, 0.f), 0u, 0u);
                }
            fence_async_smem();
            __syncwarp();
            if (tid == 288) mbar_arrive(bar_stat);
#pragma unroll 4
            for (int k = 0; k < 40; k++) asm volatile("st.global.v4.u32 [%0], {%1,%1,%1,%1};" ::"l"(of + (mb * 8 + hg) * 1280 + 32 * k + (tid - 288)), "r"(~0u) : "memory");
            asm volatile("fence.acq_rel.gpu;" ::: "memory");
            asm volatile("fence.proxy.async.global;" ::: "memory");
            __syncwarp();
            if (tid == 288) mbar_arrive(bar_done);
            TSTAMP1T(9, 288);
        } else if (w == 8) {
            asm volatile("bar.sync 3, 64;" ::: "memory");
            if (elect()) {
#pragma unroll 1
                for (int kb = A1_P0; kb < 10; kb++) {
                    if (kb < A1_NST) mbar_wait(bars + 8 * A1_PW, 0);
                    else {
                        mbar_wait(bars + 8 * (A1_NST + kb % A1_NST), ((kb / A1_NST) - 1) & 1);
                        if (layer && kb < 9) mbar_wait(bar_rd + 8 * (kb - A1_NST), 0);
                        mbar_expect_tx(bars + 8 * (kb % A1_NST), A1_STAGE);
                    }
                    issue_x(kb, kb < 5 ? kb + te.kb0 : kb - te.kb0); issue_w(kb);
                    if (kb == A1_WOAT) {
                        mbar_expect_tx(bar_wo, 8 * WOB);
                        bulk_load(sbase + A1_SM_W0, wo + hg * 8 * WOB, 2 * WOB, bar_wo);
                    }
                }
                TSTAMP1T(6, 256);
                mbar_wait(bars + 8 * (A1_NST + 3), 1);
                bulk_load(sbase + A1_SM_W3, wo + (hg * 8 + 3) * WOB, 3 * WOB, bar_wo);
            }
            __syncwarp();
        } else {
            const int j = tid - 320;
            const uint32_t tag = ld_epoch();
            if (tid == 352) sm_started(layer);
            if (layer == 0) {
                const uint4* src = reinterpret_cast<const uint4*>(x0 + (size_t)(mb * 128 + hg * 16 + (j >> 2)) * DM);
                uint4 v[20];
#pragma unroll
                for (int k = 0; k < 20; k++) v[k] = __ldg(src + (j & 3) + 4 * k);
                const float p0 = __uint_as_float(__shfl_sync(~0u, v[0].x, j & 28) << 16);
                float s[2] = {0.f, 0.f}, q[2] = {0.f, 0.f};
#pragma unroll
                for (int k = 0; k < 20; k++) {
                    const uint32_t w[4] = {v[k].x, v[k].y, v[k].z, v[k].w};
#pragma unroll
                    for (int i = 0; i < 4; i++) {
                        const float a = __uint_as_float(w[i] << 16) - p0, b = __uint_as_float(w[i] & 0xffff0000u) - p0;
                        s[0] += a; s[1] += b; q[0] = fmaf(a, a, q[0]); q[1] = fmaf(b, b, q[1]);
                    }
                }
                float s0 = s[0] + s[1], q0 = q[0] + q[1];
#pragma unroll
                for (int o = 1; o <= 2; o <<= 1) { s0 += __shfl_xor_sync(~0u, s0, o); q0 += __shfl_xor_sync(~0u, q0, o); }
                if ((j & 3) == 0) {
                    const float d = s0 * (1.0f / DM);
                    const uint32_t ms = pack2(p0 + d, sqrt_apx(rbf(rbf(fmaxf(fmaf(-d, d, q0 * (1.0f / DM)), 0.f)) + 1e-5f)));
                    asm volatile("st.global.cg.u64 [%0], %1;" ::"l"(g_rstat + mb * 128 + (j & 4) * 16 + hg * 8 + (j >> 3)), "l"(tagw(ms, tag)) : "memory");
                    g_piv[mb * 128 + hg * 16 + ((j >> 2) & 8) + (j & 4) + ((j >> 3) & 3)] = __ushort_as_bfloat16((unsigned short)ms);
                }
            }
            float o[4];
            int row;
            if (layer == 0) {
                ulonglong2 v;
#pragma unroll 1
                for (int it = 0; it < SPIN_MAX; it++) {
                    v = ld_tag2(reinterpret_cast<const ulonglong2*>(g_rstat + mb * 128) + j);
                    if (tag_ok(v, tag)) break;
                    __nanosleep(100);
                }
                o[0] = __uint_as_float((uint32_t)v.x << 16); o[1] = rcp_apx(__uint_as_float((uint32_t)v.x & 0xffff0000u));
                o[2] = __uint_as_float((uint32_t)v.y << 16); o[3] = rcp_apx(__uint_as_float((uint32_t)v.y & 0xffff0000u));
                row = 2 * j;
            } else {
                const int ch = j & 7, kg = (j >> 3) & 3;
                const unsigned char* src = stg + (j >> 5) * 8192 + (hg & 3) * 2048;
                float s[8], q[8], p0[8];
#pragma unroll
                for (int i = 0; i < 8; i++) { s[i] = 0.f; q[i] = 0.f; }
#pragma unroll 1
                for (int it = 0; it < 5; it++) {
                    uint4 v[4];
                    mbar_wait(bars + 8 * (it % A1_NST), it / A1_NST);
#pragma unroll
                    for (int k = 0; k < 4; k++) v[k] = *reinterpret_cast<const uint4*>(src + (it % A1_NST) * A1_STAGE + (4 * k + kg) * 128 + ((ch ^ ((4 * k + kg) & 7)) << 4));
                    if (it == 0) {
                        const uint4 pv = *reinterpret_cast<const uint4*>(src + (ch << 4));
                        const uint32_t w[4] = {pv.x, pv.y, pv.z, pv.w};
#pragma unroll
                        for (int i = 0; i < 4; i++) { p0[2 * i] = __uint_as_float(w[i] << 16); p0[2 * i + 1] = __uint_as_float(w[i] & 0xffff0000u); }
                    }
                    asm volatile("" :: "r"(v[0].x), "r"(v[1].x), "r"(v[2].x), "r"(v[3].x), "f"(p0[0]) : "memory");
                    __syncwarp();
                    if ((tid & 31) == 0) mbar_arrive(bar_rd + 8 * it);
#pragma unroll
                    for (int k = 0; k < 4; k++) {
                        const uint32_t w[4] = {v[k].x, v[k].y, v[k].z, v[k].w};
#pragma unroll
                        for (int i = 0; i < 4; i++) {
                            const float a = __uint_as_float(w[i] << 16) - p0[2 * i], b = __uint_as_float(w[i] & 0xffff0000u) - p0[2 * i + 1];
                            s[2 * i] += a; s[2 * i + 1] += b; q[2 * i] = fmaf(a, a, q[2 * i]); q[2 * i + 1] = fmaf(b, b, q[2 * i + 1]);
                        }
                    }
                }
#pragma unroll
                for (int i = 0; i < 4; i++) {
                    const bool up = kg & 2;
                    const float ss = __shfl_xor_sync(~0u, up ? s[i] : s[i + 4], 16), qq = __shfl_xor_sync(~0u, up ? q[i] : q[i + 4], 16);
                    s[i] = (up ? s[i + 4] : s[i]) + ss; q[i] = (up ? q[i + 4] : q[i]) + qq; p0[i] = up ? p0[i + 4] : p0[i];
                }
#pragma unroll
                for (int i = 0; i < 2; i++) {
                    const bool up = kg & 1;
                    const float ss = __shfl_xor_sync(~0u, up ? s[i] : s[i + 2], 8), qq = __shfl_xor_sync(~0u, up ? q[i] : q[i + 2], 8);
                    s[i] = (up ? s[i + 2] : s[i]) + ss; q[i] = (up ? q[i + 2] : q[i]) + qq; p0[i] = up ? p0[i + 2] : p0[i];
                }
                uint4* gp = g_halo + 86016 + mb * 512 + j;
                const float d0 = s[0] * (1.0f / 80.0f), d1 = s[1] * (1.0f / 80.0f);
                asm volatile("st.relaxed.gpu.global.v4.f32 [%0], {%1,%2,%3,%4};" ::"l"(gp + hg * 64), "f"(p0[0] + d0), "f"(fmaxf(fmaf(-d0, s[0], q[0]), 0.f)), "f"(p0[1] + d1), "f"(fmaxf(fmaf(-d1, s[1], q[1]), 0.f)) : "memory");
                __nanosleep(ST_SLEEP0);
                uint32_t pw[8][4], todo = 0xff;
#pragma unroll 1
                for (int it = 0; it < SPIN_MAX; it++) {
#pragma unroll
                    for (int k = 0; k < 8; k++)
                        if (todo >> k & 1) asm volatile("ld.relaxed.gpu.global.v4.u32 {%0,%1,%2,%3}, [%4];" : "=r"(pw[k][0]), "=r"(pw[k][1]), "=r"(pw[k][2]), "=r"(pw[k][3]) : "l"(gp + k * 64) : "memory");
#pragma unroll
                    for (int k = 0; k < 8; k++)
                        if (__all_sync(~0u, pw[k][0] != ~0u && pw[k][1] != ~0u && pw[k][2] != ~0u && pw[k][3] != ~0u)) todo &= ~(1u << k);
                    if (!todo) break;
                    __nanosleep(ST_SLEEP);
                }
#pragma unroll
                for (int r = 0; r < 2; r++) {
                    float mean = 0.f, m2 = 0.f;
#pragma unroll
                    for (int k = 0; k < 8; k++) mean += __uint_as_float(pw[k][2 * r]);
                    mean *= 0.125f;
#pragma unroll
                    for (int k = 0; k < 8; k++) {
                        const float dm = __uint_as_float(pw[k][2 * r]) - mean;
                        m2 += fmaf(80.0f * dm, dm, __uint_as_float(pw[k][2 * r + 1]));
                    }
                    o[2 * r] = rbf(mean);
                    o[2 * r + 1] = rcp_apx(rbf(sqrt_apx(rbf(rbf(m2 * (1.0f / DM)) + 1e-5f))));
                }
                row = (j >> 5) * 64 + (j & 7) * 8 + ((j >> 3) & 3) * 2;
                if (hg == 0) *reinterpret_cast<uint32_t*>(g_piv + SEQ + mb * 128 + 2 * (row & 60) + 4 * (row >> 6) + (row & 3)) = __byte_perm(__float_as_uint(o[0]), __float_as_uint(o[2]), 0x7632);
            }
#pragma unroll
            for (int r = 0; r < 2; r++)
                *reinterpret_cast<uint4*>(stg + A1_SM_XA + (row + r) * 16) = make_uint4(__byte_perm(__float_as_uint(-o[2 * r]), 0, 0x3232), __float_as_uint(-o[2 * r]) >> 16, 0u, 0u);
            *reinterpret_cast<float4*>(rst + row + (row >> 6) * 8) = make_float4(o[0], o[1], o[2], o[3]);
            fence_async_smem();
            TSTAMP1T(7, 320);
            if (tid == 320) DBGC(44);
            __syncwarp();
            if ((tid & 31) == 0) mbar_arrive(bar_stat);
        }
        if (tid == 320) DBGCAL(0);
        if (tid == 352) {
            mbar_wait(WO_LATE, 0);
            mbar_wait(bar_done, 0);
            bulk_load(sbase, wo + (hg * 8 + 6) * WOB, 2 * WOB, bar_wo);
            bulk_load(sbase + A1_SM_W0 + 2 * WOB, wo + (hg * 8 + 2) * WOB, WOB, bar_wo);
        }
        if (w < 10) {
            const int cw = w - 8;
            const uint32_t* fl = reinterpret_cast<const uint32_t*>(rsum + 2 * SEQ) + (((layer * 16 + mb) * 2 + cw) * 8 + (tid & 7)) * FSTR;
            const unsigned char* src = reinterpret_cast<const unsigned char*>(of) + mb * 163840 + cw * 10240 + (tid & 7) * 20480;
            const uint32_t sl = sbase + (cw ? A1_SM_A1 : A1_SM_A0);
            mbar_wait(cw ? bar_done : bar_kvf, 0);
            if ((tid & 31) == 0) {
                mbar_expect_tx(bar_f2 + 64 * cw + 64, 10240);
                tma_load_3d(sl + 51200, &tmR, layer ? 0 : hg * 80, layer ? hg * 80 : mb * 64, layer ? mb * 2 + cw : cw, bar_f2 + 64 * cw + 64);
            }
            __syncwarp();
            uint32_t pend = 0xffu & ~(1u << hg), v = 0;
            const uint32_t bo = wo_off((tid & 7) + ((tid & 7) < hg)) >> 4, lt = (1u << (tid & 31)) - 1;
#pragma unroll 1
            for (int it = 0; pend && it < 2 * SPIN_MAX; it++) {
                if (v != 4 && (pend >> (tid & 31) & 1)) asm volatile(A1_FLD " %0, [%1];" : "=r"(v) : "l"(fl) : "memory");
                uint32_t fr;
                asm volatile("{\n.reg .pred p;\nmbarrier.test_wait.parity.shared::cta.b64 p, [%1], 0;\nselp.b32 %0, 1, 0, p;\n}" : "=r"(fr) : "r"(bar_e2 + 16 * cw + (tid & 1) * 8) : "memory");
                fr = __ballot_sync(~0u, fr);
                uint32_t m = __ballot_sync(~0u, v == 4 || it >= A1_FSPIN) & pend;
                const int q = 8 - __popc(pend) + __popc(m & lt);
                m &= __ballot_sync(~0u, q < ((fr & 2) ? 8 : (fr & 1) ? 7 : 5));
                pend ^= m;
                if (m >> (tid & 31) & 1) DBGC(12 + cw * 8 + (tid & 7));
                if (!m) __nanosleep(A1_FSLEEP);
                else asm volatile("fence.proxy.async.global;" ::: "memory");
                if (m >> (tid & 31) & 1) {
                    bulk_load(q == 7 && !cw ? sbase + A1_SM_W0 : sl + (q < 6 ? q : q - 6) * 10240, src, 10240, bar_f2 + 64 * cw + 8 * q);
                    asm volatile("st.shared.u32 [%0], %1;" ::"r"(que + 32 * cw + 4 * q), "r"(bo) : "memory");
                    mbar_expect_tx(bar_f2 + 64 * cw + 8 * q, 10240);
                    DBGC(44 + cw * 8 + q);
                }
                __syncwarp();
            }
        }
    } else {
        if (tid == 0) {
            mbar_init(bar_stat, 3);
#pragma unroll
            for (int i = 0; i < 8; i++) mbar_init(bar_kv + 8 * i, 1);
            mbar_init(bars + 144, 1);
            mbar_init(bars + 160, 1);
#pragma unroll
            for (int i = 0; i < 5; i++) mbar_init(bar_rd + 8 * i, 2);
            asm volatile("fence.mbarrier_init.release.cluster;" ::: "memory");
        } else if (tid == 32) {
            mbar_init(bar_wo, 1); mbar_init(bar_done, 3); mbar_init(bar_pv, 4); mbar_init(bar_kvf, 8); mbar_init(bars + 240, 4);
#pragma unroll
            for (int i = 0; i < 4; i++) { mbar_init(bar_e2 + 8 * i, i == 1 ? 2 : 1); mbar_init(bars + 8 * (A1_NST + i), 2); }
            asm volatile("fence.mbarrier_init.release.cluster;" ::: "memory");
        } else if (tid == 64) {
#pragma unroll
            for (int i = 1; i <= 16; i++) mbar_init(bar_f2 + 8 * i, 1);
            asm volatile("fence.mbarrier_init.release.cluster;" ::: "memory");
        }
        asm volatile("bar.sync 0, 384;" ::: "memory");
        SPAN(1 + 4 * layer, 0);
        constexpr int on = 1;
        float acc[120];
        const int lane = tid & 31, warp = w & 7, g = lane >> 2, t = lane & 3;
        if (on) {
            SPAN(1 + 4 * layer, 1);
            TSTAMP1(0);
            if (threadIdx.x == 0) { GSTAMP(g_tim1, 15); }
            TSTAMP3(0);
            if (tid == 0) TSTAMP2(0);
            TSTAMP4(0);
            if (tid == 0) DBGC(60);
            if (layer == 0) a1_mainloop<0>(acc, sbase, bars, wg, tile); else a1_mainloop<1>(acc, sbase, bars, wg, tile);
            uint32_t ok;
            asm volatile("{\n.reg .pred p;\nmbarrier.test_wait.parity.shared::cta.b64 p, [%1], 0;\nselp.b32 %0, 1, 0, p;\n}" : "=r"(ok) : "r"(bar_stat) : "memory");
            if (tid == 128 && !ok) mbar_arrive(bars + 160);
            __syncwarp();
            mbar_wait(bar_stat, 0);
            wgmma_fence();
            wgmma_n240<0, 0>(acc, make_desc(sbase + A1_SM_XA + wg * 1024, 0, 128, 0), make_desc(sbase + A1_SM_XB, 0, 128, 0), 1);
            wgmma_commit();
            if (tid == 128 && ok) mbar_arrive(bars + 160);
            mbar_wait(bars + 8 * (A1_NST + 3), 1);
        }
        const float2* rw = rst + 16 * warp + 8 * wg;
        const float rb0 = rw[g + 8].y, ra = rw[g].y * 0.22360679774997896f, rb = rb0 * 0.22360679774997896f;
        wgmma_wait<0>();
        if ((tid & 127) == 0) mbar_arrive(bar_done);
        TSTAMP1(2);
        TSTAMP1T(13, 224);
        if ((tid & 127) == 0) DBGC(62 - wg);
        uint32_t f[2][30];
#pragma unroll
        for (int j = 10; j < 30; j++) f[1][j] = pack2(acc[4 * j + 2], acc[4 * j + 3]);
        if ((warp & 3) == 3) {
            uint4* hout = g_halo + (((layer * 16 + mb) * 8 + hg) * 2 + wg) * 168;
#pragma unroll
            for (int j = 0; j < 20; j += 4)
                asm volatile("st.relaxed.gpu.global.v4.u32 [%0], {%1,%2,%3,%4};" ::"l"(hout + 8 * j + lane), "r"(f[1][10 + j]), "r"(f[1][11 + j]), "r"(f[1][12 + j]), "r"(f[1][13 + j]) : "memory");
            if (t == 0) asm volatile("st.relaxed.gpu.global.f32 [%0], %1;" ::"l"(reinterpret_cast<float*>(hout + 160) + g), "f"(rb0) : "memory");
        }
        TSTAMP1T(12, 224);
        const uint32_t kvw = sbase + A1_SM_KV + (16 * warp + 8 * wg) * A1_KVP;
        const uint32_t mrow = kvw + (lane & 7) * A1_KVP + (lane >> 3) * 16;
#pragma unroll
        for (int j = 0; j < 20; j += 4) stsm_x4(mrow + 16 * A1_KVP + 16 * j, f[1][10 + j], f[1][11 + j], f[1][12 + j], f[1][13 + j]);
        __syncwarp();
        if (lane == 0 && (warp & 3) != 3) mbar_arrive(bar_kv + 8 * (warp + 1));
#pragma unroll
        for (int j = 0; j < 30; j++) f[0][j] = pack2(acc[4 * j], acc[4 * j + 1]);
        stsm_x4(mrow + 8 * A1_KVP + 160, f[0][20], f[0][21], f[0][22], f[0][23]);
        stsm_x4(mrow + 8 * A1_KVP + 224, f[0][24], f[0][25], f[0][26], f[0][27]);
        asm volatile("stmatrix.sync.aligned.m8n8.x2.shared.b16 [%0], {%1,%2};" ::"r"(mrow + 8 * A1_KVP + 288), "r"(f[0][28]), "r"(f[0][29]) : "memory");
#pragma unroll
        for (int j = 0; j < 10; j++) f[1][j] = pack2(acc[4 * j + 2], acc[4 * j + 3]);
        __syncwarp();
        uint32_t vb[10][2], vp[12], kp[12];
#pragma unroll
        for (int j = 0; j < 10; j += 2) ldsm_x4_t(&vb[j][0], kvw + (8 + (lane & 15)) * A1_KVP + 160 + (lane >> 4) * 16 + 16 * j);
        const bool up0 = 2 * t > g, up1 = 2 * t + 1 > g, edge = (mb | (warp & 3)) == 0;
        float rk[4];
        auto above = [&]() {
            mbar_wait(bar_kv + 8 * warp, 0);
#pragma unroll
            for (int j = 0; j < 12; j += 4) ldsm_x4(&kp[j], mrow + 16 * j);
            rk[0] = rw[2 * t - (up0 ? 8 : 0)].y; rk[1] = rw[2 * t + 1 - (up1 ? 8 : 0)].y;
#pragma unroll
            for (int j = 0; j < 12; j += 4) ldsm_x4_t(&vp[j], mrow + 160 + 16 * j - (j == 8 ? (lane & 16) * 2 : 0));
            __syncwarp();
            if (lane == 0) mbar_arrive(bar_kvf);
        };
        auto halo = [&]() {
            if (lane == 0) mbar_arrive(bar_kvf);
            const uint4* hin = g_halo + (((layer * 16 + mb - 1) * 8 + hg) * 2 + wg) * 168;
            uint32_t hv[22] = {};
            rk[0] = rw[2 * t].y; rk[1] = rw[2 * t + 1].y;
            if (mb > 0) {
#pragma unroll 1
                for (int it = 0; it < SPIN_MAX; it++) {
#pragma unroll
                    for (int k = 0; k < 20; k += 4)
                        asm volatile("ld.relaxed.gpu.global.v4.u32 {%0,%1,%2,%3}, [%4];" : "=r"(hv[k]), "=r"(hv[k + 1]), "=r"(hv[k + 2]), "=r"(hv[k + 3]) : "l"(hin + 8 * k + lane) : "memory");
                    asm volatile("ld.relaxed.gpu.global.v2.u32 {%0,%1}, [%2];" : "=r"(hv[20]), "=r"(hv[21]) : "l"(reinterpret_cast<const uint2*>(hin + 160) + t) : "memory");
                    uint32_t m = max(hv[20], hv[21]);
#pragma unroll
                    for (int k = 0; k < 20; k += 2) m = __vimax3_u32(m, hv[k], hv[k + 1]);
                    if (!__any_sync(~0u, m == ~0u)) break;
                }
            }
            if (tid == 0) mbar_arrive(bars + 144);
            if (lane == 0) DBGC(52 - 16 * wg);
#pragma unroll
            for (int j = 0; j < 10; j++) {
                kp[j] = hv[j];
                asm volatile("movmatrix.sync.aligned.m8n8.trans.b16 %0, %1;" : "=r"(vp[j]) : "r"(hv[10 + j]));
            }
            if (up0) rk[0] = __uint_as_float(hv[20]);
            if (up1) rk[1] = __uint_as_float(hv[21]);
        };
        rk[2] = rw[2 * t + (up0 ? 0 : 8)].y; rk[3] = rw[2 * t + 1 + (up1 ? 0 : 8)].y;
        uint32_t qs[4][2];
#pragma unroll
        for (int h = 0; h < 4; h++) {
            qs[h][0] = (t >> 1) == (h & 1) ? f[0][5 * (h >> 1) + 2] : 0u; qs[h][1] = (t >> 1) == (h & 1) ? f[1][5 * (h >> 1) + 2] : 0u;
            asm volatile("" : "+r"(qs[h][0]), "+r"(qs[h][1]));
        }
#pragma unroll
        for (int j = 0; j < 10; j++) asm volatile("" : "+r"(f[0][j]), "+r"(f[1][j]), "+r"(f[0][10 + j]));
        if (warp & 3) above(); else if (wg) halo();
        TSTAMP1T(10, 64);
        float sc[4][3][4];
#pragma unroll
        for (int h = 0; h < 4; h++) {
            const int jb = 5 * (h >> 1) + 3 * (h & 1), js = 5 * (h >> 1) + 2;
#pragma unroll
            for (int nt = 1; nt < 3; nt++) {
#pragma unroll
                for (int e = 0; e < 4; e++) sc[h][nt][e] = 0.f;
                mma_bf16(sc[h][nt], f[0][jb], f[1][jb], f[0][jb + 1], f[1][jb + 1], f[nt - 1][10 + jb], f[nt - 1][11 + jb]);
                mma_bf16_k8(sc[h][nt], qs[h][0], qs[h][1], f[nt - 1][10 + js]);
            }
        }
        if (tid == 128) mbar_arrive(bars + 240);
        if (warp == 0) halo();
        TSTAMP1(8);
#pragma unroll
        for (int h = 0; h < 4; h++) {
            const int jb = 5 * (h >> 1) + 3 * (h & 1), js = 5 * (h >> 1) + 2;
#pragma unroll
            for (int e = 0; e < 4; e++) sc[h][0][e] = 0.f;
            mma_bf16(sc[h][0], f[0][jb], f[1][jb], f[0][jb + 1], f[1][jb + 1], kp[jb], kp[jb + 1]);
            mma_bf16_k8(sc[h][0], qs[h][0], qs[h][1], kp[js]);
        }
        if (warp > 4) { __syncwarp(); if (lane == 0) mbar_arrive(bars + 240); }
        TSTAMP1T(3, 64);
        float p[4][4], sum[4][2];
        uint32_t lg[4][2], mx[4];
        const float rl[4] = {rk[0] * ra, rk[1] * ra, rk[2] * rb, rk[3] * rb};
        auto max2 = [](uint32_t a, uint32_t b) { uint32_t r; asm("max.bf16x2 %0, %1, %2;" : "=r"(r) : "r"(a), "r"(b)); return r; };
#pragma unroll
        for (int h = 0; h < 4; h++) {
            lg[h][0] = pack2((up0 ? sc[h][0][0] : sc[h][1][0]) * rl[0], (up0 ? sc[h][1][2] : sc[h][2][2]) * rl[2]);
            lg[h][1] = pack2((up1 ? sc[h][0][1] : sc[h][1][1]) * rl[1], (up1 ? sc[h][1][3] : sc[h][2][3]) * rl[3]);
            if (edge) {
                if (up0) lg[h][0] = __byte_perm(lg[h][0], 0xce6eu, 0x3254);
                if (up1) lg[h][1] = __byte_perm(lg[h][1], 0xce6eu, 0x3254);
            }
            mx[h] = max2(lg[h][0], lg[h][1]);
        }
#pragma unroll
        for (int o = 1; o <= 2; o <<= 1)
#pragma unroll
            for (int h = 0; h < 4; h++) mx[h] = max2(mx[h], __shfl_xor_sync(~0u, mx[h], o));
#pragma unroll
        for (int h = 0; h < 4; h++)
#pragma unroll
            for (int r = 0; r < 2; r++) {
                const float m = __uint_as_float(r ? mx[h] & 0xffff0000u : mx[h] << 16);
#pragma unroll
                for (int e = 0; e < 2; e++)
                    asm("ex2.approx.ftz.f32 %0, %1;" : "=f"(p[h][2 * r + e]) : "f"((__uint_as_float(r ? lg[h][e] & 0xffff0000u : lg[h][e] << 16) - m) * 1.4426950408889634f));
                sum[h][r] = p[h][2 * r] + p[h][2 * r + 1];
            }
#pragma unroll
        for (int o = 1; o <= 2; o <<= 1)
#pragma unroll
            for (int h = 0; h < 4; h++)
#pragma unroll
                for (int r = 0; r < 2; r++) sum[h][r] += __shfl_xor_sync(~0u, sum[h][r], o);
        TSTAMP1T(5, 64);
        const uint32_t mu = (up0 ? 0xffffu : 0u) | (up1 ? 0xffff0000u : 0u);
        uint32_t ob[10][2];
#pragma unroll
        for (int P = 0; P < 2; P++) {
            float os[2][4];
#pragma unroll
            for (int e = 0; e < 2; e++) {
                const int h = 2 * P + e;
                const float i0 = rcp_apx(sum[h][0]), i1 = rcp_apx(sum[h][1]);
                const uint32_t w0 = pack2(p[h][0] * rk[0] * i0, p[h][1] * rk[1] * i0), w1 = pack2(p[h][2] * rk[2] * i1, p[h][3] * rk[3] * i1);
#pragma unroll
                for (int dt = 0; dt < 3; dt++) {
                    const int j = 5 * P + (dt < 2 ? 3 * e + dt : 2);
                    float o[4] = {0.f, 0.f, 0.f, 0.f};
                    mma_bf16(o, w0 & ~mu, w1 & mu, 0u, w1 & ~mu, vb[j][0], vb[j][1]);
                    mma_bf16_k8(o, w0 & mu, 0u, vp[j]);
                    if (dt < 2) { ob[j][0] = pack2(o[0], o[1]); ob[j][1] = pack2(o[2], o[3]); }
                    else { os[e][0] = o[0]; os[e][1] = o[1]; os[e][2] = o[2]; os[e][3] = o[3]; }
                }
            }
#pragma unroll
            for (int k = 0; k < 4; k++) os[0][k] = t < 2 ? os[0][k] : os[1][k];
            ob[5 * P + 2][0] = pack2(os[0][0], os[0][1]); ob[5 * P + 2][1] = pack2(os[0][2], os[0][3]);
        }
        const uint32_t sl = sbase + (wg ? A1_SM_A1 : A1_SM_A0);
        const uint32_t o0 = (warp & 3) * 2048 + g * 64 + ((t ^ (g >> 1)) << 4), o1 = 8192 + (warp & 3) * 512 + g * 32 + ((t ^ ((g >> 2) << 1)) << 3);
        mbar_wait(bar_done, 0);
        if (wg == 0) mbar_wait(bar_kvf, 0);
#pragma unroll
        for (int h = 0; h < 2; h++) {
            asm volatile("st.shared.v4.u32 [%0], {%1,%2,%3,%4};" ::"r"(sl + o0 + h * 1024), "r"(ob[0][h]), "r"(ob[1][h]), "r"(ob[2][h]), "r"(ob[3][h]) : "memory");
            asm volatile("st.shared.v4.u32 [%0], {%1,%2,%3,%4};" ::"r"(sl + o0 + h * 1024 + 512), "r"(ob[4][h]), "r"(ob[5][h]), "r"(ob[6][h]), "r"(ob[7][h]) : "memory");
            asm volatile("st.shared.v2.u32 [%0], {%1,%2};" ::"r"(sl + o1 + h * 256), "r"(ob[8][h]), "r"(ob[9][h]) : "memory");
        }
        fence_async_smem();
        __syncwarp();
        TSTAMP1T(4, 64);
        TSTAMP1(1);
        TSTAMP2(1);
        const unsigned char* ot = reinterpret_cast<const unsigned char*>(of) + mb * 163840 + wg * 10240;
        if (lane == 0) {
            asm volatile("cp.async.bulk.global.shared::cta.bulk_group [%0], [%1], 2048;" ::"l"(ot + hg * 20480 + (warp & 3) * 2048), "r"(sl + (warp & 3) * 2048) : "memory");
            asm volatile("cp.async.bulk.global.shared::cta.bulk_group [%0], [%1], 512;" ::"l"(ot + hg * 20480 + 8192 + (warp & 3) * 512), "r"(sl + 8192 + (warp & 3) * 512) : "memory");
            asm volatile("cp.async.bulk.commit_group;" ::: "memory");
            if (wg == 0) mbar_arrive(bar_pv);
            asm volatile("cp.async.bulk.wait_group 0;" ::: "memory");
            asm volatile(A1_FRED " [%0], 1;" ::"l"(reinterpret_cast<uint32_t*>(rsum + 2 * SEQ) + (((layer * 16 + mb) * 2 + wg) * 8 + hg) * FSTR) : "memory");
            DBGC(4 + warp);
        }
        TSTAMP4(11);
        float ac2[40];
        const uint64_t db0 = make_desc(sbase, 1024, 256, 3), db1 = make_desc(sbase + 10240, 512, 256, 3), da0 = make_desc(sl, 16, 1024, 2), da1 = make_desc(sl + 8192, 16, 256, 3);
        const uint32_t o7 = wg ? 640 : (A1_SM_W0 - A1_SM_A0) >> 4;
        const uint32_t trow = ((lane & 7) + 8 * (lane >> 4)) * 128 + (((2 * (warp & 3) + ((lane >> 3) & 1)) ^ (lane & 7)) << 4);
        uint32_t xr[10][2];
        mbar_wait(bar_f2 + 64 * wg + 64, 0);
        if (layer == 0) {
#pragma unroll
            for (int j = 0; j < 10; j += 2) ldsm_x4(&xr[j][0], sl + 51200 + (16 * (warp & 3) + (lane & 15)) * 160 + (lane >> 4) * 16 + 16 * j);
        } else {
#pragma unroll
            for (int j = 0; j < 10; j += 2) ldsm_x4_t(&xr[j][0], sl + 51200 + trow + 1024 * j);
        }
        const uint32_t ri = __shfl_sync(~0u, layer * SEQ + (wg * 2 + ((g >> 1) & 1)) * 512 + (mb * 16 + 4 * (warp & 3) + (g >> 2)) * 2 + (g & 1), lane);
        mbar_wait(bar_wo, 0);
        if (wg) mbar_wait(bar_pv, 0);
        if (wg) asm volatile("bar.sync 2, 128;" ::: "memory"); else asm volatile("bar.sync 1, 128;" ::: "memory");
        TSTAMP2(2);
#pragma unroll
        for (int q = 0; q < 8; q++) {
            uint32_t bo = wo_off(0) >> 4;
            if (q) {
                mbar_wait(bar_f2 + 64 * wg + 8 * q, 0);
                asm volatile("ld.shared.u32 %0, [%1];" : "=r"(bo) : "r"(que + 32 * wg + 4 * q) : "memory");
                bo = __shfl_sync(~0u, bo, 0);
                TSTAMP4(q);
                if (q == 1 && (tid & 127) == 0) DBGC(29 + 8 * wg);
            }
            wgmma_fence();
#pragma unroll
            for (int j = 0; j < 5; j++) wgmma_n80(ac2, (j < 4 ? da0 : da1) + (q == 7 ? o7 : 0u) + (uint64_t)((q < 6 ? q * 640 : 0) + (j & 2) * 16 + (j & 1) * 2), (j < 4 ? db0 : db1) + bo + (uint64_t)((j & 2) * 160 + (j & 1) * 32), j || q);
            wgmma_commit();
            if (q == 0) {
                wgmma_wait<0>();
                if ((tid & 127) == 0) { mbar_arrive(bar_e2 + 16 * wg); mbar_arrive(bar_e2 + 8); }
            }
            if (q == 2 && wg) {
                wgmma_wait<1>();
                if (tid == 128) mbar_arrive(bar_e2 + 24);
            }
        }
        if ((tid & 127) == 0) DBGC(28 + wg * 8 + 7);
        TSTAMP2(3);
        wgmma_wait<0>();
        TSTAMP2(4);
        if (__any_sync(~0u, ac2[0] != ac2[0] || ac2[2] != ac2[2])) {
#pragma unroll
            for (int i = 0; i < 40; i++) ac2[i] = 0.f;
            uint32_t a[20], an[20];
            auto lda = [&](uint32_t (&r)[20], int h) {
#pragma unroll
                for (int u = 0; u < 4; u++)
                    asm volatile("ld.relaxed.gpu.global.v4.u32 {%0,%1,%2,%3}, [%4];" : "=r"(r[4 * u]), "=r"(r[4 * u + 1]), "=r"(r[4 * u + 2]), "=r"(r[4 * u + 3]) : "l"(ot + h * 20480 + o0 + u * 512) : "memory");
#pragma unroll
                for (int u = 0; u < 2; u++)
                    asm volatile("ld.relaxed.gpu.global.v2.u32 {%0,%1}, [%2];" : "=r"(r[16 + 2 * u]), "=r"(r[17 + 2 * u]) : "l"(ot + h * 20480 + o1 + u * 256) : "memory");
            };
            lda(an, 0);
#pragma unroll 5
            for (int k = lane; k < WOB / 16; k += 32)
                reinterpret_cast<uint4*>(stg + (sl - sbase))[k] = __ldcg(reinterpret_cast<const uint4*>(wo + hg * 8 * WOB) + k);
            __syncwarp();
#pragma unroll 1
            for (int h = 0; h < 8; h++) {
#pragma unroll 1
                for (int it = 0; it < SPIN_MAX; it++) {
                    uint32_t m = 0;
#pragma unroll
                    for (int k = 0; k < 20; k += 2) m = __vimax3_u32(m, an[k], an[k + 1]);
                    if (!__any_sync(~0u, m == ~0u)) break;
                    lda(an, h);
                }
#pragma unroll
                for (int k = 0; k < 20; k++) a[k] = an[k];
                lda(an, min(h + 1, 7));
                const uint32_t bp = h == hg ? sl : sbase + wo_off(h + (h < hg));
                const int r0 = 8 * ((lane & 7) >> 1) + 2 * (lane >> 3) + (lane & 1), r2 = 4 * ((lane & 7) >> 1) + 2 * ((lane >> 3) & 1) + (lane & 1);
#pragma unroll
                for (int n = 0; n < 10; n++) {
                    uint32_t b[12];
                    ldsm_x4_t(b, bp + (n >> 1) * 1024 + r0 * 32 + (((n ^ (r0 >> 2)) & 1) << 4));
                    ldsm_x4_t(b + 4, bp + 5120 + (n >> 1) * 1024 + r0 * 32 + (((n ^ (r0 >> 2)) & 1) << 4));
                    ldsm_x4_t(b + 8, bp + 10240 + (n >> 1) * 512 + r2 * 32 + (((n ^ (r2 >> 2)) & 1) << 4));
                    mma_bf16(ac2 + 4 * n, a[0], a[8], a[1], a[9], b[0], b[1]); mma_bf16(ac2 + 4 * n, a[2], a[10], a[3], a[11], b[2], b[3]);
                    mma_bf16(ac2 + 4 * n, a[4], a[12], a[5], a[13], b[4], b[5]); mma_bf16(ac2 + 4 * n, a[6], a[14], a[7], a[15], b[6], b[7]);
                    mma_bf16(ac2 + 4 * n, a[16], a[18], a[17], a[19], b[8], b[9]);
                }
            }
        }
#pragma unroll
        for (int j = 0; j < 10; j++)
#pragma unroll
            for (int hh = 0; hh < 2; hh++) {
                const uint32_t a = pack2(ac2[4 * j + 2 * hh], ac2[4 * j + 2 * hh + 1]);
                const __nv_bfloat162 r = __hadd2_rn(*reinterpret_cast<const __nv_bfloat162*>(&xr[j][hh]), *reinterpret_cast<const __nv_bfloat162*>(&a));
                xr[j][hh] = *reinterpret_cast<const uint32_t*>(&r);
            }
        const uint32_t so = sl + 30720;
#pragma unroll
        for (int j = 0; j < 10; j += 2) stsm_x4_t(so + trow + 1024 * j, xr[j][0], xr[j][1], xr[j + 1][0], xr[j + 1][1]);
        fence_async_smem();
        if (wg) asm volatile("bar.sync 2, 128;" ::: "memory"); else asm volatile("bar.sync 1, 128;" ::: "memory");
        TSTAMP2(5);
        if ((tid & 127) == 0) {
            asm volatile("cp.async.bulk.tensor.2d.global.shared::cta.bulk_group [%0, {%1, %2}], [%3];" ::"l"(&tmX1), "r"(mb * 128 + 64 * wg), "r"(hg * 80), "r"(so) : "memory");
            asm volatile("cp.async.bulk.commit_group;" ::: "memory");
        }
        __syncwarp();
        const float p0 = *(volatile const float*)&rw[g].x, p1 = *(volatile const float*)&rw[g + 8].x;
        float s[3][4] = {};
        const uint32_t pp[2] = {__byte_perm(__float_as_uint(p0), 0, 0x3232), __byte_perm(__float_as_uint(p1), 0, 0x3232)};
#pragma unroll
        for (int j = 0; j < 10; j += 2) {
            const uint32_t d0 = sub2(xr[j][0], pp[0]), d1 = sub2(xr[j][1], pp[1]), d2 = sub2(xr[j + 1][0], pp[0]), d3 = sub2(xr[j + 1][1], pp[1]);
            mma_bf16(s[0], xr[j][0], xr[j][1], xr[j + 1][0], xr[j + 1][1], 0x3f803f80u, 0x3f803f80u);
            mma_bf16(s[1], d0, d1, d2, d3, d0, d2);
            mma_bf16(s[2], d0, d1, d2, d3, d1, d3);
        }
        if (t == (g >> 1)) {
            float2* rp = rsum + ri;
            asm volatile("red.relaxed.gpu.global.add.v2.f32 [%0], {%1, %2};" ::"l"(rp), "f"(fmaf(-80.f, p0, s[0][0])), "f"((g & 1) ? s[1][1] : s[1][0]) : "memory");
            asm volatile("red.relaxed.gpu.global.add.v2.f32 [%0], {%1, %2};" ::"l"(rp + 4), "f"(fmaf(-80.f, p1, s[0][2])), "f"((g & 1) ? s[2][3] : s[2][2]) : "memory");
        }
        asm volatile("cp.async.bulk.wait_group.read 0;" ::: "memory");
        TSTAMP2(6);
        if (tid == 0) DBGC(63);
        if (tid == 128) DBGC(28);
        if (tid == 0) DBGCAL(2);
        GSTAMP(g_tim1, 14);
        SPAN(1 + 4 * layer, 3);
    }
}

static int h_nsm;
static void* h_sym[11];
static TileTab h_tab;
static CUtensorMap h_tmX0, h_tmX1, h_tmR0, h_tmR1, h_tmX1st, h_tmOut, h_tmWq, h_tmWo, h_tmWt;
typedef CUresult (*PFN_encodeTiled)(CUtensorMap*, CUtensorMapDataType, cuuint32_t, void*, const cuuint64_t*, const cuuint64_t*,
                                    const cuuint32_t*, const cuuint32_t*, CUtensorMapInterleave, CUtensorMapSwizzle,
                                    CUtensorMapL2promotion, CUtensorMapFloatOOBfill);
static void make_tmap(CUtensorMap* tm, const void* ptr, uint64_t cols, uint64_t rows, uint32_t bc, uint32_t br, CUtensorMapSwizzle sw, uint64_t pitch = 0, uint64_t hi = 0, uint32_t bh = 2) {
    static PFN_encodeTiled fn = nullptr;
    if (!fn) {
        void* p = nullptr; cudaDriverEntryPointQueryResult qr;
        cudaGetDriverEntryPoint("cuTensorMapEncodeTiled", &p, cudaEnableDefault, &qr);
        fn = (PFN_encodeTiled)p;
    }
    if (br == 0) {
        cuuint64_t dims[5] = {16, 2, rows / 8, 4, cols / 16}; cuuint64_t strides[4] = {cols * 2, cols * 16, cols * 4, 32};
        cuuint32_t box[5] = {16, 2, bc, 4, 5}; cuuint32_t es[5] = {1, 1, 1, 1, 1};
        fn(tm, CU_TENSOR_MAP_DATA_TYPE_BFLOAT16, 5, const_cast<void*>(ptr), dims, strides, box, es, CU_TENSOR_MAP_INTERLEAVE_NONE, sw,
           CU_TENSOR_MAP_L2_PROMOTION_L2_128B, CU_TENSOR_MAP_FLOAT_OOB_FILL_NONE);
        return;
    }
    if (bh == 0) {
        cuuint64_t dims[5] = {64, 64, 2, 16, 10}; cuuint64_t strides[4] = {pitch * 2, hi * 2, cols * 2, rows * 2};
        cuuint32_t box[5] = {64, 64, 2, 1, 1}; cuuint32_t es[5] = {1, 1, 1, 1, 1};
        fn(tm, CU_TENSOR_MAP_DATA_TYPE_BFLOAT16, 5, const_cast<void*>(ptr), dims, strides, box, es, CU_TENSOR_MAP_INTERLEAVE_NONE, sw,
           CU_TENSOR_MAP_L2_PROMOTION_L2_128B, CU_TENSOR_MAP_FLOAT_OOB_FILL_NONE);
        return;
    }
    if (hi) {
        cuuint64_t dims[3] = {cols, rows, hi == 64 ? 32u : hi == 16 ? 120u : 2u}; cuuint64_t strides[2] = {pitch * 2, hi * 2};
        cuuint32_t box[3] = {bc, br, bh}; cuuint32_t es[3] = {1, 1, 1};
        fn(tm, CU_TENSOR_MAP_DATA_TYPE_BFLOAT16, 3, const_cast<void*>(ptr), dims, strides, box, es, CU_TENSOR_MAP_INTERLEAVE_NONE, sw,
           CU_TENSOR_MAP_L2_PROMOTION_L2_128B, CU_TENSOR_MAP_FLOAT_OOB_FILL_NONE);
        return;
    }
    cuuint64_t dims[2] = {cols, rows}; cuuint64_t strides[1] = {(pitch ? pitch : cols) * 2};
    cuuint32_t box[2] = {bc, br}; cuuint32_t es[2] = {1, 1};
    fn(tm, CU_TENSOR_MAP_DATA_TYPE_BFLOAT16, 2, const_cast<void*>(ptr), dims, strides, box, es, CU_TENSOR_MAP_INTERLEAVE_NONE, sw,
       CU_TENSOR_MAP_L2_PROMOTION_L2_128B, CU_TENSOR_MAP_FLOAT_OOB_FILL_NONE);
}
template <typename... Args>
static void launch_pdl(void (*kern)(Args...), int grid, int block, int smem, Args... args) {
    cudaLaunchConfig_t cfg = {};
    cfg.gridDim = dim3(grid); cfg.blockDim = dim3(block); cfg.dynamicSmemBytes = smem; cfg.stream = cudaStreamPerThread;
    cudaLaunchAttribute at[1];
    at[0].id = cudaLaunchAttributeProgrammaticStreamSerialization; at[0].val.programmaticStreamSerializationAllowed = 1;
    cfg.attrs = at; cfg.numAttrs = 1;
    cudaLaunchKernelEx(&cfg, kern, args...);
}
static void launch_stage(int k, void* const* d_in, void* d_out) {
    const KgIn kg = {(const bf16*)d_in[4], (const bf16*)d_in[5], (const bf16*)d_in[6], (const bf16*)d_in[7], (const bf16*)d_in[8], (const bf16*)d_in[0], (const bf16*)d_in[1], (const bf16*)d_in[2],
                      (uint4*)h_sym[0], (uint4*)h_sym[1], (uint4*)h_sym[2], (uint4*)h_sym[3], (uint4*)h_sym[4], (float*)h_sym[5]};
    switch (k) {
        case 0: kgen_kernel<<<128, 512, KG_SMEM, cudaStreamPerThread>>>(kg, h_tmWq, h_tmWo, h_tmWt); break;
        case 1: launch_pdl(a1_kernel, h_nsm, A1_THREADS, A1_SMEM, 0, (const bf16*)d_in[0], (const unsigned char*)h_sym[1], (const unsigned char*)h_sym[2], (float2*)h_sym[4], (uint4*)h_sym[6], h_tmX0, h_tmR0, h_tmX1st, h_tab); break;
        case 3: launch_pdl(conv_kernel, DM / CV_CPB, CV_THREADS, CV_SMEM, (const bf16*)d_in[9], 0, (const uint4*)h_sym[7], (const float4*)h_sym[4], (const bf16*)h_sym[8], (bf16*)h_sym[9], (const uint4*)h_sym[0], (bf16*)h_sym[10], h_tmOut); break;
        case 5: launch_pdl(a1_kernel, h_nsm, A1_THREADS, A1_SMEM, 1, (const bf16*)d_in[0], (const unsigned char*)h_sym[1], (const unsigned char*)h_sym[2], (float2*)h_sym[4], (uint4*)h_sym[6], h_tmX1, h_tmR1, h_tmX1st, h_tab); break;
        case 7: launch_pdl(conv_kernel, DM / CV_CPB, CV_THREADS, CV_SMEM, (const bf16*)d_in[9], 1, (const uint4*)h_sym[7] + SEQ / 8, (const float4*)h_sym[4] + SEQ / 2, (const bf16*)h_sym[8], (bf16*)h_sym[10], (const uint4*)h_sym[0], (bf16*)h_sym[10], h_tmOut); break;
        default: break;
    }
}
static int n_stage_kernels() { return 9; }
static const char* stage_name(int k) { const char* n[] = {"kgen", "a1", "a2", "conv", "tr", "a1", "a2", "conv", "tr"}; return n[k]; }

extern "C" void kernel_launch(void* const* d_in, const int* in_sizes, int n_in, void* d_out, int out_size) {
    (void)in_sizes; (void)n_in; (void)out_size;
    static const void *p_in = nullptr, *p_w1 = nullptr, *p_w2 = nullptr, *p_out = nullptr;
    if (p_in != d_in[0] || p_w1 != d_in[1] || p_w2 != d_in[2] || p_out != d_out) {
        cudaFuncSetAttribute(conv_kernel, cudaFuncAttributeMaxDynamicSharedMemorySize, CV_SMEM);
        cudaFuncSetAttribute(kgen_kernel, cudaFuncAttributeMaxDynamicSharedMemorySize, KG_SMEM);
        cudaFuncSetAttribute(a1_kernel, cudaFuncAttributeMaxDynamicSharedMemorySize, A1_SMEM);
        int dev; cudaGetDevice(&dev); cudaDeviceGetAttribute(&h_nsm, cudaDevAttrMultiProcessorCount, dev);
        if (h_nsm != 132) h_nsm = 128;
        h_tab.ns = h_nsm == 132 ? 132 : ~0u;
        for (int i = 0; i < 264; i++) {
            const int h = (i - 64) >> 1;
            const int t = i >= 132 ? i - 132 : i < 64 ? ((i >> 1) & 7) * 16 + (i >> 4) * 2 + (i & 1) : i < 120 ? (1 + h % 7) * 16 + 8 + (h / 7) * 2 + (i & 1) : i < 124 ? 128 : i - 116;
            const int hg = (4 * (t >> 6) + (t & 3)) & 7;
            h_tab.e[i] = {(unsigned char)((t >> 2) & 15), (unsigned char)hg, (unsigned char)(5 * (hg >> 2)), (unsigned char)t, (uint32_t)(hg * 10 * WQ_STAGE)};
        }
        cudaGetSymbolAddress(&h_sym[0], g_tap); cudaGetSymbolAddress(&h_sym[1], g_wq); cudaGetSymbolAddress(&h_sym[2], g_wo);
        cudaGetSymbolAddress(&h_sym[3], g_halo); cudaGetSymbolAddress(&h_sym[4], g_sum); cudaGetSymbolAddress(&h_sym[5], g_csp); cudaGetSymbolAddress(&h_sym[6], g_of);
        cudaGetSymbolAddress(&h_sym[7], g_piv); cudaGetSymbolAddress(&h_sym[8], g_x1T); cudaGetSymbolAddress(&h_sym[9], g_xcT); cudaGetSymbolAddress(&h_sym[10], g_yT);
        void *px1, *px2;
        cudaGetSymbolAddress(&px1, g_x1T); cudaGetSymbolAddress(&px2, g_xcT);
        make_tmap(&h_tmX0, d_in[0], 128 * 640, 64, 64, 64, CU_TENSOR_MAP_SWIZZLE_128B, 1280, 640, 0);
        make_tmap(&h_tmX1, px2, 128, 64 * XCP, 64, 64, CU_TENSOR_MAP_SWIZZLE_128B, XCP, 64, 0);
        make_tmap(&h_tmR0, d_in[0], 640, 1024, 80, 64, CU_TENSOR_MAP_SWIZZLE_NONE, 1280, 640, 1);
        make_tmap(&h_tmR1, px2, 64, 640, 64, 80, CU_TENSOR_MAP_SWIZZLE_128B, XCP, 64, 1);
        make_tmap(&h_tmX1st, px1, 2048, 640, 64, 80, CU_TENSOR_MAP_SWIZZLE_128B, XCP);
        make_tmap(&h_tmWq, d_in[1], 16, 640, 16, 32, CU_TENSOR_MAP_SWIZZLE_32B, 1920, 16, 5);
        make_tmap(&h_tmWo, d_in[2], 640, 640, 4, 0, CU_TENSOR_MAP_SWIZZLE_32B);
        make_tmap(&h_tmWt, d_in[2], 640, 640, 2, 0, CU_TENSOR_MAP_SWIZZLE_32B);
        make_tmap(&h_tmOut, d_out, 640, 2048, 80, 8, CU_TENSOR_MAP_SWIZZLE_NONE);
        p_in = d_in[0]; p_w1 = d_in[1]; p_w2 = d_in[2]; p_out = d_out;
    }
    for (int k = 0; k < n_stage_kernels(); k++) launch_stage(k, d_in, d_out);
}
```

```cpp
#include <cuda_runtime.h>
#include <cuda_bf16.h>
#include <stdint.h>
#include <cuda.h>

typedef __nv_bfloat16 bf16;

constexpr int SEQ = 2048;
constexpr int DM = 640;
constexpr int NMODE = 192;

__device__ __forceinline__ float bf2f(bf16 v) { return __bfloat162float(v); }
__device__ __forceinline__ float rbf(float v) {
    uint32_t r;
    asm("cvt.rn.bf16x2.f32 %0, %1, %2;" : "=r"(r) : "f"(v), "f"(0.f));
    return __uint_as_float(r);
}
__device__ __forceinline__ uint32_t pack2(float lo, float hi) {
    __nv_bfloat162 t = __floats2bfloat162_rn(lo, hi);
    return *reinterpret_cast<uint32_t*>(&t);
}
__device__ __forceinline__ void pdl_sync() {
    asm volatile("griddepcontrol.wait;" ::: "memory");
    asm volatile("griddepcontrol.launch_dependents;" ::: "memory");
}
__device__ __forceinline__ float sqrt_apx(float v) { float r; asm("sqrt.approx.ftz.f32 %0, %1;" : "=f"(r) : "f"(v)); return r; }
__device__ __forceinline__ float rcp_apx(float v) { float r; asm("rcp.approx.ftz.f32 %0, %1;" : "=f"(r) : "f"(v)); return r; }
__device__ __forceinline__ uint32_t smem_u32(const void* p) { return (uint32_t)__cvta_generic_to_shared(p); }

constexpr int TPAD = 32, TAPB = 320 * 8;
__device__ __align__(128) uint4 g_tap[DM * 128];
#define XPAD 64
constexpr int XCP = SEQ + XPAD;
__device__ __align__(128) bf16 g_x1T[DM * XCP];
__device__ __align__(128) bf16 g_xcT[DM * XCP];
__device__ __align__(128) uint4 g_of[128 * 1280];
constexpr int WQ_STAGE = 240 * 128, WOB = 80 * 160;
__device__ __align__(128) uint4 g_wq[8 * 10 * WQ_STAGE / 16];
__device__ __align__(128) uint4 g_wo[64 * WOB / 16];
__device__ __align__(16) float g_csp[10 * 1920];
#define FSTR 32
__device__ __align__(128) float2 g_sum[2 * SEQ + 256 * FSTR];
__device__ __align__(16) bf16 g_piv[2 * SEQ];
__device__ __align__(128) bf16 g_yT[DM * XCP];
__device__ uint32_t g_epoch;
__device__ __align__(16) unsigned long long g_rstat[SEQ];
__device__ __align__(128) uint4 g_halo[640 * 148];
__device__ __forceinline__ unsigned long long tagw(uint32_t payload, uint32_t tag) { return ((unsigned long long)tag << 32) | payload; }
__device__ __forceinline__ ulonglong2 ld_tag2(const ulonglong2* p) {
    ulonglong2 v;
    asm volatile("ld.relaxed.gpu.global.v2.u64 {%0, %1}, [%2];" : "=l"(v.x), "=l"(v.y) : "l"(p) : "memory");
    return v;
}
__device__ __forceinline__ bool tag_ok(ulonglong2 v, uint32_t tag) { return (uint32_t)(v.x >> 32) == tag && (uint32_t)(v.y >> 32) == tag; }
__device__ __forceinline__ uint32_t ld_epoch() { uint32_t v; asm volatile("ld.relaxed.gpu.global.u32 %0, [%1];" : "=r"(v) : "l"(&g_epoch) : "memory"); return v + 1; }
constexpr int SPIN_MAX = 1 << 20;
__device__ uint32_t g_started[4];
__device__ __forceinline__ void sm_started(int slot) { asm volatile("red.relaxed.gpu.global.add.u32 [%0], 1;" ::"l"(g_started + slot) : "memory"); }
__device__ __noinline__ void sm_idle(int slot) {
    if (threadIdx.x) return;
    sm_started(slot);
    const uint32_t want = ld_epoch() * gridDim.x;
    pdl_sync();
#pragma unroll 1
    for (int it = 0; it < SPIN_MAX; it++) {
        uint32_t v;
        asm volatile("ld.relaxed.gpu.global.u32 %0, [%1];" : "=r"(v) : "l"(g_started + slot) : "memory");
        if ((int)(v - want) >= 0) break;
        __nanosleep(100);
    }
}
struct TileTab { uint32_t ns, pad; struct { unsigned char mb, hg, kb0, tile; uint32_t woff; } __align__(8) e[264]; };
__device__ __forceinline__ bool elect() {
    uint32_t p;
    asm volatile("{\n.reg .pred p;\nelect.sync _|p, 0xffffffff;\nselp.b32 %0, 1, 0, p;\n}" : "=r"(p));
    return p;
}
#define DBG_SYMS
#define TSTAMP(i)
#define TSTAMP1(i)
#define TSTAMP1T(i, t)
#define TSTAMP1X(i, t)
#define SPAN(k, i)
#define GSTAMP(arr, i)
#define TSTAMP2(i)
#define TSTAMP3(i)
#define TSTAMP4(i)
#define TSTAMPK(i, t)
#define TSTAMPC(i)
#define DBGC(i)
#define DBGV(i, v)
#define DBGCAL(i)

__device__ __forceinline__ void mma_bf16(float* d, uint32_t a0, uint32_t a1, uint32_t a2, uint32_t a3, uint32_t b0, uint32_t b1) {
    asm volatile("mma.sync.aligned.m16n8k16.row.col.f32.bf16.bf16.f32 {%0,%1,%2,%3}, {%4,%5,%6,%7}, {%8,%9}, {%0,%1,%2,%3};"
                 : "+f"(d[0]), "+f"(d[1]), "+f"(d[2]), "+f"(d[3]) : "r"(a0), "r"(a1), "r"(a2), "r"(a3), "r"(b0), "r"(b1));
}
__device__ __forceinline__ void mma_bf16_k8(float* d, uint32_t a0, uint32_t a1, uint32_t b0) {
    asm volatile("mma.sync.aligned.m16n8k8.row.col.f32.bf16.bf16.f32 {%0,%1,%2,%3}, {%4,%5}, {%6}, {%0,%1,%2,%3};"
                 : "+f"(d[0]), "+f"(d[1]), "+f"(d[2]), "+f"(d[3]) : "r"(a0), "r"(a1), "r"(b0));
}
__device__ __forceinline__ void ldsm_x4(uint32_t* r, uint32_t addr) {
    asm volatile("ldmatrix.sync.aligned.m8n8.x4.shared.b16 {%0,%1,%2,%3}, [%4];"
                 : "=r"(r[0]), "=r"(r[1]), "=r"(r[2]), "=r"(r[3]) : "r"(addr));
}

__device__ __forceinline__ void ldsm_x4_t(uint32_t* r, uint32_t addr) {
    asm volatile("ldmatrix.sync.aligned.m8n8.x4.trans.shared.b16 {%0,%1,%2,%3}, [%4];"
                 : "=r"(r[0]), "=r"(r[1]), "=r"(r[2]), "=r"(r[3]) : "r"(addr));
}
__device__ __forceinline__ void mbar_init(uint32_t bar, int count) { asm volatile("mbarrier.init.shared::cta.b64 [%0], %1;" ::"r"(bar), "r"(count)); }
__device__ __forceinline__ void mbar_arrive(uint32_t bar) { asm volatile("mbarrier.arrive.shared::cta.b64 _, [%0];" ::"r"(bar) : "memory"); }
__device__ __forceinline__ void mbar_wait(uint32_t bar, uint32_t parity) {
    asm volatile("{\n.reg .pred p;\nWAIT_LOOP:\n"
                 "mbarrier.try_wait.parity.shared::cta.b64 p, [%0], %1;\n"
                 "@p bra.uni WAIT_DONE;\nbra.uni WAIT_LOOP;\nWAIT_DONE:\n}" ::"r"(bar), "r"(parity) : "memory");
}

__device__ __forceinline__ void mbar_expect_tx(uint32_t bar, uint32_t bytes) {
    asm volatile("mbarrier.arrive.expect_tx.shared::cta.b64 _, [%0], %1;" ::"r"(bar), "r"(bytes) : "memory");
}
__device__ __forceinline__ void tma_load_2d(uint32_t dst, const void* tmap, int c0, int c1, uint32_t bar) {
    asm volatile("cp.async.bulk.tensor.2d.shared::cluster.global.mbarrier::complete_tx::bytes [%0], [%1, {%3, %4}], [%2];"
                 ::"r"(dst), "l"(tmap), "r"(bar), "r"(c0), "r"(c1) : "memory");
}
__device__ __forceinline__ void tma_load_3d(uint32_t dst, const void* tmap, int c0, int c1, int c2, uint32_t bar) {
    asm volatile("cp.async.bulk.tensor.3d.shared::cluster.global.mbarrier::complete_tx::bytes [%0], [%1, {%3, %4, %5}], [%2];"
                 ::"r"(dst), "l"(tmap), "r"(bar), "r"(c0), "r"(c1), "r"(c2) : "memory");
}
__device__ __forceinline__ void fence_async_smem() { asm volatile("fence.proxy.async.shared::cta;" ::: "memory"); }
__device__ __forceinline__ void bulk_load(uint32_t dst, const void* src, uint32_t bytes, uint32_t bar) {
    asm volatile("cp.async.bulk.shared::cluster.global.mbarrier::complete_tx::bytes [%0], [%1], %2, [%3];"
                 ::"r"(dst), "l"(src), "r"(bytes), "r"(bar) : "memory");
}
__device__ __forceinline__ void tma_store_2d(const void* tmap, int c0, int c1, uint32_t src) {
    asm volatile("cp.async.bulk.tensor.2d.global.shared::cta.bulk_group [%0, {%1, %2}], [%3];" ::"l"(tmap), "r"(c0), "r"(c1), "r"(src) : "memory");
    asm volatile("cp.async.bulk.commit_group;" ::: "memory");
    asm volatile("cp.async.bulk.wait_group.read 0;" ::: "memory");
}
__device__ __forceinline__ void stsm_x4(uint32_t addr, uint32_t r0, uint32_t r1, uint32_t r2, uint32_t r3) {
    asm volatile("stmatrix.sync.aligned.m8n8.x4.shared.b16 [%0], {%1,%2,%3,%4};" ::"r"(addr), "r"(r0), "r"(r1), "r"(r2), "r"(r3) : "memory");
}
__device__ __forceinline__ void stsm_x4_t(uint32_t addr, uint32_t r0, uint32_t r1, uint32_t r2, uint32_t r3) {
    asm volatile("stmatrix.sync.aligned.m8n8.x4.trans.shared.b16 [%0], {%1,%2,%3,%4};" ::"r"(addr), "r"(r0), "r"(r1), "r"(r2), "r"(r3) : "memory");
}
__device__ __forceinline__ void prefetch_tmap(const void* tmap) { asm volatile("prefetch.tensormap [%0];" ::"l"(tmap) : "memory"); }

__device__ __forceinline__ float2 cexp_at(float wr2, float wi, float p) {
    float er;
    asm("ex2.approx.ftz.f32 %0, %1;" : "=f"(er) : "f"(wr2 * p));
    float th = wi * p;
    const float k = rintf(th * 0.15915494309189535f);
    th = fmaf(k, -6.2831854820251465f, th);
    th = fmaf(k, 1.7484555314695172e-7f, th);
    return make_float2(er * __cosf(th), er * __sinf(th));
}
__device__ __forceinline__ float2 cmul(float2 a, float2 b) {
    return make_float2(fmaf(a.x, b.x, -a.y * b.y), fmaf(a.x, b.y, a.y * b.x));
}
__device__ __forceinline__ float2 csqr(float2 a) { return make_float2(fmaf(a.x, a.x, -a.y * a.y), (a.x + a.x) * a.y); }
__device__ __forceinline__ uint32_t packh(float2 v) {
    uint32_t r;
    asm("cvt.rn.f16x2.f32 %0, %1, %2;" : "=r"(r) : "f"(v.y), "f"(v.x));
    return r;
}
__device__ __forceinline__ void mma_f16(float* d, uint32_t a0, uint32_t a1, uint32_t a2, uint32_t a3, uint32_t b0, uint32_t b1) {
    asm volatile("mma.sync.aligned.m16n8k16.row.col.f32.f16.f16.f32 {%0,%1,%2,%3}, {%4,%5,%6,%7}, {%8,%9}, {%0,%1,%2,%3};"
                 : "+f"(d[0]), "+f"(d[1]), "+f"(d[2]), "+f"(d[3]) : "r"(a0), "r"(a1), "r"(a2), "r"(a3), "r"(b0), "r"(b1));
}

struct KgIn { const bf16 *logA, *Aim, *Cre, *Cim, *logdt, *dsk, *x, *wqkv, *wo; uint4 *tap, *wq, *wop, *halo, *sum; float* csp; };
constexpr int KG_THREADS = NMODE / 2;

constexpr int KG_BUF = 15 * 12288, KG_BAR = KG_BUF + 6 * 5120, KG_SMEM = KG_BAR + 64;
__global__ void __launch_bounds__(512, 1) kgen_kernel(const KgIn in, const __grid_constant__ CUtensorMap tmWq, const __grid_constant__ CUtensorMap tmWo,
                                                        const __grid_constant__ CUtensorMap tmWt) {
    extern __shared__ __align__(1024) uint4 tabs[];
#define KG_ROT 0
    const int lane = threadIdx.x & 31, w16 = (__shfl_sync(~0u, threadIdx.x >> 5, 0) + KG_ROT) & 15, grp = w16 / 3, warp = w16 - 3 * grp;
    const int d = blockIdx.x * 5 + grp, tid = warp * 32 + lane;
    uint4* tab = tabs + grp * (3 * 768);
    SPAN(0, 0); SPAN(0, 1);
    TSTAMPK(0, 0);
    asm volatile("griddepcontrol.launch_dependents;" ::: "memory");
    if (w16 == 15) {
        const uint32_t b0 = smem_u32(tab), wbar = b0 + 6 * 5120;
        const int blk = blockIdx.x, nq = blk < 112 ? 4 : 2, nj = nq + (blk < 64 ? 1 : 2);
        auto fetch = [&](int i) {
            const uint32_t dst = b0 + i * 5120, bar = wbar + 8 * i;
            if (i < nq) {
                const int p = blk + 64 * (i & 2), kb = p / 24;
                mbar_expect_tx(bar, 5120);
                tma_load_3d(dst, &tmWq, 0, kb * 64 + (i & 1) * 32, (p - 24 * kb) * 5, bar);
            } else if (i < nj) {
                const int o = i == nq ? blk : 255 - blk;
                mbar_expect_tx(bar, o < 128 ? 5120 : 2560);
                asm volatile("cp.async.bulk.tensor.5d.shared::cluster.global.mbarrier::complete_tx::bytes [%0], [%1, {%3, %3, %4, %3, %5}], [%2];"
                             ::"r"(dst), "l"(o < 128 ? &tmWo : &tmWt), "r"(bar), "r"(0), "r"((o & 7) * 10 + (o >> 6) * 4), "r"(((o >> 3) & 7) * 5) : "memory");
            }
        };
        const bool one = elect();
        if (one) {
#pragma unroll
            for (int i = 0; i < 6; i++) mbar_init(wbar + 8 * i, 1);
            asm volatile("fence.mbarrier_init.release.cluster;" ::: "memory");
#pragma unroll
            for (int i = 0; i < 6; i++) fetch(i);
        }
        __syncwarp();
#pragma unroll
        for (int i = 1; i <= 5; i++) asm volatile("bar.arrive %0, 128;" ::"r"(i) : "memory");
        if (one) {
#pragma unroll 1
            for (int i = 0; i < nj; i++) {
                const int p = blk + 64 * (i & 2), kb = p / 24, hg = p & 7, sec = (p - 24 * kb) >> 3, o = i == nq ? blk : 255 - blk, cg = (o >> 3) & 7, hb = o & 7;
                const unsigned char* dst = i < nq ? reinterpret_cast<unsigned char*>(in.wq) + (hg * 10 + (hg < 4 ? kb : kb < 5 ? kb + 5 : kb - 5)) * WQ_STAGE + ((i & 1) * 3 + sec) * 5120
                                                  : reinterpret_cast<unsigned char*>(in.wop) + (cg * 8 + (hb == cg ? 0 : hb + (hb < cg))) * WOB + (o >> 6) * 5120;
                mbar_wait(wbar + 8 * i, 0);
                if (i == 0) TSTAMPK(2, (15 - KG_ROT) * 32);
                if (i == 3) TSTAMPK(5, (15 - KG_ROT) * 32);
                asm volatile("cp.async.bulk.global.shared::cta.bulk_group [%0], [%1], %2;" ::"l"(dst), "r"(b0 + i * 5120), "r"(i < nq || o < 128 ? 5120 : 2560) : "memory");
            }
            asm volatile("cp.async.bulk.commit_group;" ::: "memory");
            asm volatile("cp.async.bulk.wait_group.read 0;" ::: "memory");
        }
        TSTAMPK(11, (15 - KG_ROT) * 32);
        return;
    }
    const bf16 pdt = in.logdt[d], pdsk = in.dsk[d];
    const uint32_t pla = reinterpret_cast<const uint32_t*>(in.logA)[d * KG_THREADS + tid], pai = reinterpret_cast<const uint32_t*>(in.Aim)[d * KG_THREADS + tid];
    const uint32_t pcr = reinterpret_cast<const uint32_t*>(in.Cre)[d * KG_THREADS + tid], pci = reinterpret_cast<const uint32_t*>(in.Cim)[d * KG_THREADS + tid];
    const bf16* pfq = tid < 30 ? in.wqkv + (size_t)(d * 30 + tid) * 64 : tid < 40 ? in.wo + (size_t)(d * 10 + tid - 30) * 64 : in.x + (size_t)(d * 32 + tid - 40) * 64;
#define KG_PF 0
    if (tid < (KG_PF == 3 ? 0 : KG_PF ? 40 : 72)) asm volatile("prefetch.global.L2 [%0];" ::"l"(pfq));
    asm volatile("st.global.v4.u32 [%0], {%1,%1,%1,%1};" ::"l"(in.halo + d * 148 + tid), "r"(~0u));
    if (tid < 52) asm volatile("st.global.v4.u32 [%0], {%1,%1,%1,%1};" ::"l"(in.halo + d * 148 + 96 + tid), "r"(~0u));
    else if (w16 == 2) {
        if (lane < 16) in.sum[blockIdx.x * 16 + lane] = make_uint4(0, 0, 0, 0);
        else if (lane < 20) reinterpret_cast<uint32_t*>(in.sum + 2048)[(blockIdx.x * 4 + lane - 16) * FSTR] = 0;
    }
    const uint32_t tw = smem_u32(tab) + warp * 12288;
    const int g = lane >> 2, t = lane & 3;
    const uint32_t sta = tw + lane * 128 + ((2 * (lane & 3) + ((lane >> 2) & 1)) << 4);
    const uint32_t lda = tw + t * 128 + ((g ^ (2 * t)) << 4);
    const uint32_t stb = tw + lane * 8, ldb = tw + g * 512 + (g & 3) * 32 + t * 8;
    auto sts4 = [&](int e, int off, uint32_t a, uint32_t b, uint32_t c, uint32_t dd) {
        asm volatile("st.shared.v4.u32 [%0], {%1,%2,%3,%4};" ::"r"((sta ^ (e << 4)) + off), "r"(a), "r"(b), "r"(c), "r"(dd) : "memory");
    };
    auto lds4 = [&](int sp, int off, uint32_t* r) {
        asm volatile("ld.shared.v4.u32 {%0,%1,%2,%3}, [%4];" : "=r"(r[0]), "=r"(r[1]), "=r"(r[2]), "=r"(r[3]) : "r"((lda ^ ((sp & 1) << 4)) + sp * 512 + off) : "memory");
    };
    const float dt = rbf(expf(bf2f(pdt)));
    float2 C[2], y1[2], z8[2], y128[2];
    float cmax = 0.f;
#pragma unroll
    for (int m = 0; m < 2; m++) {
        const float wr2 = -rbf(expf(__uint_as_float(m ? pla & 0xffff0000u : pla << 16))) * dt * 1.4426950408889634f;
        const float wi = __uint_as_float(m ? pai & 0xffff0000u : pai << 16) * dt;
        C[m] = make_float2(__uint_as_float(m ? pcr & 0xffff0000u : pcr << 16) * dt, -__uint_as_float(m ? pci & 0xffff0000u : pci << 16) * dt);
        cmax = fmaxf(cmax, fmaxf(fabsf(C[m].x), fabsf(C[m].y)));
        y1[m] = cexp_at(wr2, -wi, 1.f); z8[m] = cexp_at(wr2, wi, 8.f); y128[m] = cexp_at(wr2, -wi, 128.f);
    }
    const int ex = min(max((int)(__reduce_max_sync(~0u, __float_as_uint(cmax)) >> 23), 20), 240);
    const float scale = __uint_as_float((uint32_t)(127 + 10 + 127 - ex) << 23), unscale = 2.0f * __uint_as_float((uint32_t)(ex - 10) << 23);
    TSTAMPK(4, 64);
    if (KG_PF >= 2 && tid >= 40 && tid < 72) asm volatile("prefetch.global.L2 [%0];" ::"l"(pfq));
    float k2048 = 0.f;
    float acc[5][4];
#pragma unroll
    for (int j = 0; j < 5; j++)
#pragma unroll
        for (int k = 0; k < 4; k++) acc[j][k] = 0.f;
    uint32_t af[8][4];
    {
        float2 h0[2], h1[2], g0[2], g1[2], g2[2], g2b[2], g3[2], g4[2], y2[2], y4[2];
#pragma unroll
        for (int m = 0; m < 2; m++) {
            h0[m] = make_float2(1.f, 0.f); h1[m] = csqr(csqr(csqr(z8[m])));
            g0[m] = make_float2(C[m].x * scale, C[m].y * scale);
            g1[m] = cmul(g0[m], y128[m]);
            const float2 y256 = csqr(y128[m]), y512 = csqr(y256);
            g2b[m] = g2[m] = cmul(g0[m], y256); g3[m] = cmul(g0[m], y512); g4[m] = cmul(g3[m], y512);
            y2[m] = csqr(y1[m]); y4[m] = csqr(y2[m]);
            const float2 y1024 = csqr(y512);
            k2048 += fmaf(g4[m].x, y1024.x, -g4[m].y * y1024.y);
        }
#pragma unroll
        for (int e = 0; e < 8; e++) {
            sts4(e, 0, packh(h0[0]), packh(h1[0]), packh(h0[1]), packh(h1[1]));
            sts4(e, 4096, packh(g0[0]), packh(g0[1]), packh(g1[0]), packh(g1[1]));
#pragma unroll
            for (int m = 0; m < 2; m++)
                if (e < 7) { h0[m] = e ? cmul(h0[m], z8[m]) : z8[m]; h1[m] = cmul(h1[m], z8[m]); g0[m] = cmul(g0[m], y1[m]); g1[m] = cmul(g1[m], y1[m]); }
            if (e < 5) k2048 += __shfl_xor_sync(~0u, k2048, 1 << e);
        }
        if (KG_PF == 1 && tid >= 40 && tid < 72) asm volatile("prefetch.global.L2 [%0];" ::"l"(pfq));
        __syncwarp();
#pragma unroll
        for (int e = 0; e < 8; e++) {
            uint32_t b[4];
            lds4(e, 0, af[e]); lds4(e, 4096, b);
            sts4(e, 8192, packh(g2[0]), packh(g2[1]), packh((e & 1) ? cmul(g3[0], y4[0]) : g3[0]), packh((e & 1) ? cmul(g3[1], y4[1]) : g3[1]));
            asm volatile("st.shared.v2.u32 [%0], {%1,%2};" ::"r"((stb ^ ((e & 3) << 5)) + e * 512), "r"(packh(g4[0])), "r"(packh(g4[1])) : "memory");
#pragma unroll
            for (int m = 0; m < 2; m++)
                if (e < 7) {
                    g2[m] = e == 3 ? cmul(g2b[m], y128[m]) : cmul(g2[m], y2[m]);
                    if (e & 1) g3[m] = cmul(g3[m], y128[m]);
                    g4[m] = cmul(g4[m], y128[m]);
                }
            mma_f16(acc[0], af[e][0], af[e][1], af[e][2], af[e][3], b[0], b[1]);
            mma_f16(acc[1], af[e][0], af[e][1], af[e][2], af[e][3], b[2], b[3]);
        }
    }
    TSTAMPK(6, 64);
    __syncwarp();
#pragma unroll
    for (int sp = 0; sp < 8; sp++) {
        uint32_t c[4], e0, e1;
        lds4(sp, 8192, c);
        asm volatile("ld.shared.v2.u32 {%0,%1}, [%2];" : "=r"(e0), "=r"(e1) : "r"(ldb ^ (sp << 5)) : "memory");
        mma_f16(acc[2], af[sp][0], af[sp][1], af[sp][2], af[sp][3], c[0], c[1]);
        mma_f16(acc[3], af[sp][0], af[sp][1], af[sp][2], af[sp][3], c[2], c[3]);
        mma_f16(acc[4], af[sp][0], af[sp][1], af[sp][2], af[sp][3], e0, e1);
    }
    {
        float* Pp = reinterpret_cast<float*>(tab + warp * 768);
        auto sw = [](int i) { return i ^ ((i >> 2) & 24); };
#pragma unroll
        for (int h = 0; h < 2; h++) {
            const int b = g + 8 * h;
            *reinterpret_cast<float2*>(Pp + sw(8 * b + 2 * t)) = make_float2(acc[0][2 * h] * unscale, acc[0][2 * h + 1] * unscale);
            *reinterpret_cast<float2*>(Pp + 128 + sw(8 * b + 2 * t)) = make_float2(acc[1][2 * h] * unscale, acc[1][2 * h + 1] * unscale);
            *reinterpret_cast<float2*>(Pp + 256 + sw(4 * b + 2 * (t & 1) + 64 * (t >> 1))) = make_float2(acc[2][2 * h] * unscale, acc[2][2 * h + 1] * unscale);
            *reinterpret_cast<float2*>(Pp + 384 + sw(2 * b + 32 * t)) = make_float2(acc[3][2 * h] * unscale, acc[3][2 * h + 1] * unscale);
            Pp[512 + sw(b + 32 * t)] = acc[4][2 * h] * unscale;
            Pp[512 + sw(b + 32 * t + 16)] = acc[4][2 * h + 1] * unscale;
        }
        if (lane == 0) Pp[640] = k2048 * unscale;
    }
    TSTAMPK(7, 64);
    asm volatile("bar.sync %0, 128;" ::"r"(grp + 1) : "memory");
    TSTAMPK(9, 64);
    const float* Kp = reinterpret_cast<const float*>(tab);
    auto ksum = [&](int i) -> float { return (Kp[i] + Kp[3072 + i]) + Kp[6144 + i]; };
    auto ksum4 = [&](int q) -> float4 {
        q ^= (q >> 2) & 6;
        const float4 a = reinterpret_cast<const float4*>(Kp)[q], b = reinterpret_cast<const float4*>(Kp)[768 + q], c = reinterpret_cast<const float4*>(Kp)[1536 + q];
        return make_float4((a.x + b.x) + c.x, (a.y + b.y) + c.y, (a.z + b.z) + c.z, (a.w + b.w) + c.w);
    };
    {
        uint2* E4 = reinterpret_cast<uint2*>(in.tap + d * 128);
        float4 v = ksum4(tid), u = ksum4(96 + min(tid, 64));
        const float cor = rbf(ksum(tid == 95 ? 384 : 512));
        if (tid == 0) v.x += bf2f(pdsk);
        if (tid == 95) v.w -= cor;
        if (tid == 31) u.w -= cor;
        const uint32_t lo = pack2(v.x, v.y), hi = pack2(v.z, v.w);
        if (tid < 64) {
            E4[6 + tid] = make_uint2(lo, hi);
            E4[(tid < 32 ? 159 : 209 - 32) + tid] = make_uint2(pack2(u.x, u.y), pack2(u.z, u.w));
        } else {
            const uint32_t nx = __shfl_down_sync(~0u, lo, 1);
            in.tap[d * 128 + 35 + tid - 64] = make_uint4(__byte_perm(lo, 0, 0x1010), __byte_perm(lo, hi, 0x5432), __byte_perm(hi, 0, 0x1010), __byte_perm(hi, tid == 95 ? 0u : nx, 0x5432));
            if (tid == 64) E4[241] = make_uint2(pack2(u.x, 0.f), 0u);
        }
    }
    TSTAMPK(10, 64);
    if (warp < (blockIdx.x < 112 ? 2 : 1)) {
        const uint32_t sb = smem_u32(tabs);
        mbar_wait(sb + KG_BAR + 16 * warp, 0); mbar_wait(sb + KG_BAR + 16 * warp + 8, 0);
        uint32_t w[4][4];
        float cs[4] = {0.f, 0.f, 0.f, 0.f};
#pragma unroll
        for (int a = 0; a < 4; a++)
            ldsm_x4_t(w[a], sb + KG_BUF + warp * 10240 + grp * 1024 + ((lane >> 4) * 8 + (lane & 7)) * 32 + ((((lane >> 3) ^ (lane >> 2)) & 1) << 4) + (a >> 1) * 5120 + (a & 1) * 512);
#pragma unroll
        for (int a = 0; a < 4; a++) mma_bf16(cs, w[a][0], w[a][1], w[a][2], w[a][3], 0x3f803f80u, 0x3f803f80u);
        if (t < 2) in.csp[(blockIdx.x + 128 * warp) * 80 + grp * 16 + g + 8 * t] = t ? cs[2] : cs[0];
    }
    SPAN(0, 3);
}

#define CV_LD __ldcg
#define CV_LDX __ldcg
#define CV_SLEEP 100
#define CV_HAND 15
constexpr int CV_CPB = 5;
constexpr int CV_THREADS = 512;
constexpr int UPADF = 256;
constexpr int ULEN = UPADF + SEQ;
constexpr int XLEN = SEQ + 16;
constexpr int BX_5 = 0, BX_3 = 3264, BX_9 = 6528, BX_7 = 8960, BX_LEN = 11392;
constexpr int CV_SM_U = 0;
constexpr int CV_SM_T = CV_CPB * ULEN * 2;
constexpr int CV_SM_B = CV_SM_T + CV_CPB * TAPB;
constexpr int CV_SM_X = CV_SM_B + CV_CPB * BX_LEN;
constexpr int CV_SM_Y = (CV_SM_X + CV_CPB * XLEN * 2 + 127) & ~127;
constexpr int CV_SM_CNT = CV_SM_Y + CV_CPB * 4096;
constexpr int CV_SM_O = CV_SM_CNT + 128;
constexpr int CV_SMEM = CV_SM_O + 20480;
static_assert(ULEN % 256 == 0 && CV_SM_B % 128 == 0 && CV_SM_CNT % 128 == 0, "layout");

__device__ __forceinline__ uint32_t sub2(uint32_t x, uint32_t m) {
    const __nv_bfloat162 d = __hsub2(*reinterpret_cast<const __nv_bfloat162*>(&x), *reinterpret_cast<const __nv_bfloat162*>(&m));
    return *reinterpret_cast<const uint32_t*>(&d);
}
__device__ __forceinline__ uint32_t add2(uint32_t x, uint32_t y) {
    const __nv_bfloat162 d = __hadd2_rn(*reinterpret_cast<const __nv_bfloat162*>(&x), *reinterpret_cast<const __nv_bfloat162*>(&y));
    return *reinterpret_cast<const uint32_t*>(&d);
}
__device__ __forceinline__ void wgmma_fence() { asm volatile("wgmma.fence.sync.aligned;" ::: "memory"); }
__device__ __forceinline__ void wgmma_commit() { asm volatile("wgmma.commit_group.sync.aligned;" ::: "memory"); }
template <int N> __device__ __forceinline__ void wgmma_wait() { asm volatile("wgmma.wait_group.sync.aligned %0;" ::"n"(N) : "memory"); }
__device__ __forceinline__ uint64_t make_desc(uint32_t addr, uint32_t lbo, uint32_t sbo, uint32_t mode) {
    return (uint64_t)((addr & 0x3FFFF) >> 4) | ((uint64_t)(lbo >> 4) << 16) | ((uint64_t)(sbo >> 4) << 32) | ((uint64_t)mode << 62);
}
__device__ __forceinline__ void wgmma_rs64(float (&d)[32], uint2 hi, uint2 lo, uint64_t db, int acc) {
    asm volatile("{\n.reg .pred p;\nsetp.ne.b32 p, %37, 0;\nwgmma.mma_async.sync.aligned.m64n64k16.f32.bf16.bf16 {%0,%1,%2,%3,%4,%5,%6,%7,%8,%9,%10,%11,%12,%13,%14,%15,%16,%17,%18,%19,%20,%21,%22,%23,%24,%25,%26,%27,%28,%29,%30,%31}, {%32,%33,%34,%35}, %36, p, 1, 1, 0;\n}"
                 : "+f"(d[0]), "+f"(d[1]), "+f"(d[2]), "+f"(d[3]), "+f"(d[4]), "+f"(d[5]), "+f"(d[6]), "+f"(d[7]), "+f"(d[8]), "+f"(d[9]), "+f"(d[10]), "+f"(d[11]), "+f"(d[12]), "+f"(d[13]), "+f"(d[14]), "+f"(d[15]),
                   "+f"(d[16]), "+f"(d[17]), "+f"(d[18]), "+f"(d[19]), "+f"(d[20]), "+f"(d[21]), "+f"(d[22]), "+f"(d[23]), "+f"(d[24]), "+f"(d[25]), "+f"(d[26]), "+f"(d[27]), "+f"(d[28]), "+f"(d[29]), "+f"(d[30]), "+f"(d[31])
                 : "r"(hi.x), "r"(hi.y), "r"(lo.x), "r"(lo.y), "l"(db), "r"(acc));
}
__device__ __forceinline__ int usw(int ch) { return ch ^ ((ch >> 3) & 3); }
__global__ void __launch_bounds__(CV_THREADS, 1) conv_kernel(int layer, const uint4* __restrict__ piv, const float4* __restrict__ sum, const bf16* __restrict__ x1T,
                                                             bf16* __restrict__ dst, const uint4* __restrict__ tap, bf16* __restrict__ yT, const __grid_constant__ CUtensorMap tmOut) {
    extern __shared__ __align__(1024) unsigned char sm[];
    SPAN(3 + 4 * layer, 0);
    bf16* Us = reinterpret_cast<bf16*>(sm + CV_SM_U);
    bf16* Xs = reinterpret_cast<bf16*>(sm + CV_SM_X);
#define CV_IDX int tid; asm volatile("mov.u32 %0, %tid.x;" : "=r"(tid)); \
    const int lane = tid & 31, warp = __shfl_sync(~0u, tid >> 5, 0), g = lane >> 2, ti = lane & 3; \
    const uint32_t* E4 = reinterpret_cast<const uint32_t*>(sm + CV_SM_O) + 307 + 2 * g - ti; (void)E4;
    const int d0 = blockIdx.x * CV_CPB, tile = blockIdx.x; (void)tile;
    const uint32_t cnt = smem_u32(sm + CV_SM_CNT);
    auto task_list = [](int w) {
        const uint32_t a = w < 8 ? (w < 4 ? 0x01021A18u : 0x08001B19u) : (w < 12 ? 0x0B030C04u : 0x14130A12u), b = w < 4 ? 0x101CFFFFu : w < 8 ? 0x0911FFFFu : ~0u;
        return __byte_perm(a, b, 0x4040 + 0x11 * (w & 3)) | 0xffff0000u;
    };
    uint32_t f4[20], f8[18];
    bool have = false;
    TSTAMP1X(9, 256);
    if (threadIdx.x >= 256) {
        CV_IDX
        const int t2 = tid - 256, t7 = tid & 127, wgu = (warp >> 2) & 1;
        if (t2 == 0) {
            mbar_init(cnt + 48, 1);
            asm volatile("fence.mbarrier_init.release.cluster;" ::: "memory");
            mbar_expect_tx(cnt + 48, CV_CPB * 2048);
            bulk_load(smem_u32(sm + CV_SM_O), tap + d0 * 128, CV_CPB * 2048, cnt + 48);
        } else if (lane == 0) {
            if (warp < 15) mbar_init(cnt + 8 * (warp - 9), warp == 14 ? 8 : 4);
            else if (layer) prefetch_tmap(&tmOut);
        }
        if (t2 < 227) {
            const int k = t2;
            const int off = k < 18 ? CV_SM_B + BX_5 + 8 * k : k < 37 ? CV_SM_B + BX_3 + 8 * (k - 18) : k < 69 ? CV_SM_B + BX_9 + 8 * (k - 37) : k < 101 ? CV_SM_B + BX_7 + 8 * (k - 69)
                          : k < 165 ? CV_SM_U + 8 * (k - 101) : k < 197 ? CV_SM_T + 8 * (k - 165) : CV_SM_T + 145 * 16 + 8 * (k - 197);
            const int str = k < 101 ? BX_LEN : k < 165 ? ULEN * 2 : TAPB;
#pragma unroll
            for (int c = 0; c < CV_CPB; c++) *reinterpret_cast<uint2*>(sm + off + c * str) = make_uint2(0, 0);
        }
        fence_async_smem();
        asm volatile("bar.arrive 6, 512;" ::: "memory");
        asm volatile("bar.sync 1, 256;" ::: "memory");
        TSTAMP1X(10, 256);
        asm volatile("setmaxnreg.inc.sync.aligned.u32 136;");
        mbar_wait(cnt + 48, 0);
        TSTAMP1X(11, 256);
        {
            uint32_t w[3][4];
            const int cx = wgu ? min(t7, 4) : 4, rx = wgu ? 144 : 16 + t7;
#pragma unroll
            for (int k = 0; k < 3; k++) {
                const uint32_t* E2 = reinterpret_cast<const uint32_t*>(sm + CV_SM_O) + (k < 2 ? 512 * (wgu + 2 * k) + t7 + 11 : 512 * cx + rx - 5);
                w[k][0] = E2[0]; w[k][1] = E2[1]; w[k][2] = E2[128]; w[k][3] = E2[129];
                if (k < 2 ? t7 == 0 : rx == 16) w[k][2] = 0;
                if (k == 2 && wgu) w[k][1] = 0;
            }
#pragma unroll
            for (int k = 0; k < 3; k++)
                *reinterpret_cast<uint4*>(sm + CV_SM_T + (k < 2 ? (wgu + 2 * k) * TAPB + (t7 + 16) * 16 : cx * TAPB + rx * 16)) =
                    make_uint4(__byte_perm(w[k][1], w[k][0], 0x7610), __byte_perm(w[k][3], w[k][2], 0x7610), __byte_perm(w[k][1], 0, 0x1032), __byte_perm(w[k][3], 0, 0x1032));
        }
        asm volatile("bar.sync 1, 256;" ::: "memory");
        const uint2* Tc = reinterpret_cast<const uint2*>(sm + CV_SM_T + wgu * TAPB) + TPAD - 16 + 8 * (warp & 3) + g - 2 * ti;
        uint2 fa[18][2];
#pragma unroll
        for (int m = 0; m < 18; m++) { fa[m][0] = Tc[16 * m]; fa[m][1] = Tc[16 * m - 8]; }
        TSTAMP1X(12, 256);
        uint32_t ya = smem_u32(sm + CV_SM_Y) + wgu * 4096 + usw(4 * lane + (warp & 3)) * 16;
        uint64_t db = make_desc(smem_u32(Us + wgu * ULEN + UPADF + 16), 16, 512, 2);
        if (wgu) asm volatile("bar.sync 3, 384;" ::: "memory");
#pragma unroll 1
        for (int c = wgu; c < CV_CPB; c += 2) {
            float acc[32];
            asm volatile("bar.sync %0, %1;" ::"r"(c ? 4 + wgu : 2), "r"(c ? 256 : 384) : "memory");
            TSTAMPC(1 + 3 * c);
            wgmma_fence();
#pragma unroll
            for (int m = 0; m < 18; m++) {
                wgmma_rs64(acc, fa[m][0], fa[m][1], db - (uint64_t)(2 * m), m);
                if (m == CV_HAND && c < 4) asm volatile("bar.arrive %0, 256;" ::"r"(5 - wgu) : "memory");
            }
            wgmma_commit();
            asm volatile("griddepcontrol.launch_dependents;" ::: "memory");
            TSTAMPC(2 + 3 * c);
            wgmma_wait<0>();
            TSTAMPC(3 + 3 * c);
            Tc += 2 * TAPB / 8;
            if (c < 3) {
#pragma unroll
                for (int m = 0; m < 18; m++) { fa[m][0] = Tc[16 * m]; fa[m][1] = Tc[16 * m - 8]; }
            }
            uint32_t w[8];
#pragma unroll
            for (int j = 0; j < 8; j++) w[j] = j ? pack2(acc[4 * j] + acc[4 * j - 2], acc[4 * j + 1] + acc[4 * j - 1]) : pack2(acc[0], acc[1]);
            stsm_x4_t(ya, w[0], w[1], w[2], w[3]);
            stsm_x4_t(ya + 2048, w[4], w[5], w[6], w[7]);
            __syncwarp();
            if (lane == 0) mbar_arrive(cnt + 8 * c);
            ya += 8192; db += ULEN / 4;
        }
        TSTAMP1X(6, 256);
    } else {
        asm volatile("setmaxnreg.dec.sync.aligned.u32 120;");
        CV_IDX
        const uint4* ppv = piv + tid;
        const float4* psv = sum + tid;
        const uint2* pxv = reinterpret_cast<const uint2*>(x1T + (size_t)d0 * XCP) + (tid >> 4) * 32 + (tid & 15);
        asm volatile("st.shared.u64 [%0], %1;" ::"r"(smem_u32(Xs) + tid * 16), "l"((uint64_t)ppv ^ (uint64_t)psv ^ (uint64_t)pxv) : "memory");
        pdl_sync();
        SPAN(3 + 4 * layer, 1);
        TSTAMP(0);
        if (tid == 0) TSTAMPC(0);
        if (threadIdx.x == 0) { GSTAMP(g_tim, 15); }
        float4 sv[4];
#pragma unroll
        for (int k = 0; k < 4; k++) sv[k] = CV_LD(psv + 256 * k);
        const uint4 pv = CV_LD(ppv);
        uint2 xe[CV_CPB], xo[CV_CPB];
#pragma unroll
        for (int c = 0; c < CV_CPB; c++) { xe[c] = CV_LDX(pxv + c * (XCP / 4)); xo[c] = CV_LDX(pxv + c * (XCP / 4) + 16); }
        asm volatile("bar.sync 6, 512;" ::: "memory");
        mbar_wait(cnt + 48, 0);
        uint32_t zero;
        {
            const uint32_t tasks = task_list(warp);
            const volatile uint32_t* e4 = E4 + 512 * ((tasks & 0x18 ? tasks : tasks >> 8) & 7);
#pragma unroll
            for (int k = 0; k < 20; k++) f4[k] = e4[4 * k];
#pragma unroll
            for (int k = 0; k < 18; k++) f8[k] = e4[107 - g + 4 * k];
            have = true;
            zero = e4[-20];
        }
        const float idm = __uint_as_float(zero) + 1.0f / DM;
        uint32_t mw[4];
        float rs[8];
#pragma unroll
        for (int k = 0; k < 4; k++) {
            const uint32_t pw = (k == 0 ? pv.x : k == 1 ? pv.y : k == 2 ? pv.z : pv.w) | zero;
            const float d0_ = sv[k].x * idm, d1_ = sv[k].z * idm;
            mw[k] = pack2(__uint_as_float(pw << 16) + d0_, __uint_as_float(pw & 0xffff0000u) + d1_);
            const uint32_t vr = pack2(fmaxf(fmaf(-d0_, d0_, sv[k].y * idm), 0.f), fmaxf(fmaf(-d1_, d1_, sv[k].w * idm), 0.f));
            const uint32_t ve = pack2(__uint_as_float(vr << 16) + 1e-5f, __uint_as_float(vr & 0xffff0000u) + 1e-5f);
            const uint32_t sd = pack2(sqrt_apx(__uint_as_float(ve << 16)), sqrt_apx(__uint_as_float(ve & 0xffff0000u)));
            rs[2 * k] = rcp_apx(__uint_as_float(sd << 16)); rs[2 * k + 1] = rcp_apx(__uint_as_float(sd & 0xffff0000u));
        }
        if (rs[0] != 123.f) TSTAMP(13);
        const uint32_t ua = smem_u32(Us) + usw(tid + UPADF / 8) * 16;
        uint32_t uw[CV_CPB][4];
#pragma unroll
        for (int c = 0; c < CV_CPB; c++) {
            const uint32_t e0 = sub2(xe[c].x, mw[0]), e1 = sub2(xe[c].y, mw[1]), o0 = sub2(xo[c].x, mw[2]), o1 = sub2(xo[c].y, mw[3]);
            uw[c][0] = pack2(__uint_as_float(e0 << 16) * rs[0], __uint_as_float(o0 << 16) * rs[4]); uw[c][1] = pack2(__uint_as_float(e0 & 0xffff0000u) * rs[1], __uint_as_float(o0 & 0xffff0000u) * rs[5]);
            uw[c][2] = pack2(__uint_as_float(e1 << 16) * rs[2], __uint_as_float(o1 << 16) * rs[6]); uw[c][3] = pack2(__uint_as_float(e1 & 0xffff0000u) * rs[3], __uint_as_float(o1 & 0xffff0000u) * rs[7]);
            asm volatile("st.shared.v4.u32 [%0], {%1,%2,%3,%4};" ::"r"(ua + c * ULEN * 2), "r"(uw[c][0]), "r"(uw[c][1]), "r"(uw[c][2]), "r"(uw[c][3]) : "memory");
            if (c == 0) {
                fence_async_smem();
                asm volatile("bar.arrive 2, 384;" ::: "memory");
                zero = *(const volatile uint32_t*)(E4 - 20);
#pragma unroll
                for (int k = 0; k < 4; k++) mw[k] |= zero;
            }
        }
        fence_async_smem();
        asm volatile("bar.sync 3, 384;" ::: "memory");
        TSTAMP(1);
#pragma unroll
        for (int c = 0; c < CV_CPB; c++) *reinterpret_cast<uint4*>(Xs + c * XLEN + tid * 8) = make_uint4(xe[c].x, xe[c].y, xo[c].x, xo[c].y);
        if (warp != 6) {
            const int chunk = warp == 7 ? lane - 32 : tid;
            uint32_t ea = smem_u32(Us) + usw(chunk + UPADF / 8 + (lane ? 1 : warp == 7 ? 0 : -1)) * 16, bx = smem_u32(sm + CV_SM_B) + chunk * 16;
            const int on = warp < 6 || lane == 31, edge = (lane + 1) & 30;
            auto sts = [&](uint32_t a, const float* b) {
                asm volatile("{\n.reg .pred p;\nsetp.ne.s32 p, %5, 0;\n@p st.shared.v4.u32 [%0], {%1,%2,%3,%4};\n}"
                             ::"r"(a), "r"(pack2(b[0], b[1])), "r"(pack2(b[2], b[3])), "r"(pack2(b[4], b[5])), "r"(pack2(b[6], b[7])), "r"(on) : "memory");
            };
            if (warp == 7) {
#pragma unroll
                for (int k = 0; k < 20; k++) uw[k >> 2][k & 3] = 0;
            }
#pragma unroll 1
            for (int c = 0; c < CV_CPB; c++) {
                uint32_t w[9], ed[4];
                asm volatile("{\n.reg .pred p;\nsetp.eq.s32 p, %5, 0;\n@p ld.shared.v4.u32 {%0,%1,%2,%3}, [%4];\n}" : "=r"(ed[0]), "=r"(ed[1]), "=r"(ed[2]), "=r"(ed[3]) : "r"(ea), "r"(edge) : "memory");
#pragma unroll
                for (int k = 0; k < 4; k++) w[3 + k] = uw[0][k];
#pragma unroll
                for (int k = 0; k < 3; k++) { w[k] = __shfl_up_sync(~0u, w[4 + k], 1); if (lane == 0) w[k] = ed[1 + k]; }
#pragma unroll
                for (int k = 0; k < 2; k++) { w[7 + k] = __shfl_down_sync(~0u, w[3 + k], 1); if (lane == 31) w[7 + k] = ed[k]; }
                float v[18], b[11];
#pragma unroll
                for (int k = 0; k < 9; k++) { v[2 * k] = __uint_as_float(w[k] << 16); v[2 * k + 1] = __uint_as_float(w[k] & 0xffff0000u); }
#pragma unroll
                for (int k = 0; k < 11; k++) b[k] = v[k + 1];
#pragma unroll
                for (int k = 2; k < 17; k++) v[k] += v[k + 1];
#pragma unroll
                for (int k = 0; k < 11; k++) b[k] += v[k + 2];
                sts(bx + BX_3 + 160, b);
#pragma unroll
                for (int k = 1; k < 11; k++) b[k] += v[k + 4];
                sts(bx + BX_5 + 160, b + 3);
                if ((warp & 6) != 4) {
#pragma unroll
                    for (int k = 1; k < 10; k++) b[k] += v[k + 6];
                    sts(bx + BX_7 + 272, b + 2);
#pragma unroll
                    for (int k = 1; k < 9; k++) b[k] += v[k + 8];
                    sts(bx + BX_9 + 272, b + 1);
                }
#pragma unroll
                for (int k = 0; k < 16; k++) uw[k >> 2][k & 3] = uw[(k >> 2) + 1][k & 3];
                ea += ULEN * 2; bx += BX_LEN;
            }
        }
        __syncwarp();
        if (lane == 0) mbar_arrive(cnt + 40);
        TSTAMP(2);
        if (layer == 0) {
#pragma unroll
            for (int c = 0; c < CV_CPB; c++) reinterpret_cast<uint4*>(yT + (size_t)(d0 + c) * XCP)[tid] = make_uint4(~0u, ~0u, ~0u, ~0u);
        } else if (blockIdx.x == 0 && tid == 192) g_epoch = ld_epoch();
        __syncwarp();
    }
    {
        CV_IDX
        uint32_t tasks = task_list(warp);
        uint32_t off2, off3, offc, offd;
        {
            const int mat = lane >> 3, r = lane & 7;
            const int j2 = 13 + (r ^ 1) + 8 * (mat >> 1), j3 = j2 + 2, i0 = 8 * (mat & 1);
            off2 = (j2 & 1) ? BX_3 + (4 * j2 + i0 + 84) * 2 : BX_5 + (4 * j2 + i0 + 80) * 2;
            off3 = ((j3 & 1) ? BX_7 : BX_9) + (8 * j3 + i0 + 136) * 2;
            offc = usw(16 * (mat >> 1) + 2 * r + (mat & 1)) * 16;
            offd = usw(16 * mat + 2 * r + 2) * 16;
        }
        mbar_wait(cnt + 40, 0);
#pragma unroll 1
        for (; (tasks & 0xff) != 0xff; tasks >>= 8) {
            const int c = tasks & 7, Q = (tasks >> 3) & 3, b0 = 4 * Q;
            const uint32_t bbase = smem_u32(sm + CV_SM_B + c * BX_LEN);
            const uint32_t kk = reinterpret_cast<const uint32_t*>(sm + CV_SM_O)[512 * c + (Q ? 418 : 318)];
            unsigned char* yq = sm + CV_SM_Y + c * 4096 + Q * 1024;
            uint4 yv[2], xv[2];
            if (Q) {
                if (!have) {
                    const uint32_t* e4 = E4 + 512 * c;
#pragma unroll
                    for (int k = 0; k < 20; k++) f4[k] = e4[4 * k];
                    if (Q > 1) {
#pragma unroll
                        for (int k = 0; k < 10; k++) f8[k] = e4[107 - g + 4 * k];
                    }
                }
                have = false;
                float acc[4][4];
#pragma unroll
                for (int j = 0; j < 4; j++)
#pragma unroll
                    for (int k = 0; k < 4; k++) acc[j][k] = 0.f;
                {
                    const uint32_t ab = bbase + off2 + (2 * b0 - 2) * 128;
                    uint32_t a[3][4];
                    ldsm_x4_t(a[0], ab);
                    ldsm_x4_t(a[1], ab - 128);
#pragma unroll
                    for (int kp = 0; kp < 16; kp++) {
                        if (kp == 9 && Q == 1) break;
                        if (kp < 7 || (kp < 14 && Q > 1)) ldsm_x4_t(a[(kp + 2) % 3], ab - (kp + 2) * 128);
#pragma unroll
                        for (int j = 0; j < 4; j++) {
                            const int ee = 2 * j - 6 + kp;
                            if (ee >= 0 && ee <= 9) mma_bf16(acc[j], a[kp % 3][0], a[kp % 3][1], a[kp % 3][2], a[kp % 3][3], f4[2 * ee + 1], f4[2 * ee]);
                        }
                    }
                }
                TSTAMP(7);
                if (Q > 1) {
                    const uint32_t ab = bbase + off3 + (b0 - 6) * 256;
                    uint32_t a[3][4];
                    ldsm_x4_t(a[0], ab);
                    ldsm_x4_t(a[1], ab - 256);
#pragma unroll
                    for (int kp = 0; kp < 9; kp++) {
                        if (kp == 5 && Q == 2) break;
                        if (kp < 3 || (kp < 7 && Q == 3)) ldsm_x4_t(a[(kp + 2) % 3], ab - (kp + 2) * 256);
#pragma unroll
                        for (int j = 0; j < 4; j++) {
                            const int dl = j - 3 + kp;
                            if (dl >= 0 && dl <= 8) mma_bf16(acc[j], a[kp % 3][0], a[kp % 3][1], a[kp % 3][2], a[kp % 3][3], f8[2 * dl + 1], f8[2 * dl]);
                        }
                    }
                    const int e = g - 2 * ti;
                    const uint32_t ub = smem_u32(Us + c * ULEN + UPADF) + (Q - 2) * 1024;
                    const uint32_t P = e == -5 ? kk & 0xffffu : e == -4 ? kk << 16 : 0u, S = e == 3 ? kk & 0xffffu : e == 4 ? kk << 16 : 0u;
                    uint32_t bq[12];
                    ldsm_x4(bq, ub + offc); ldsm_x4(bq + 4, ub + offc + 512); ldsm_x4(bq + 8, ub + offd);
#pragma unroll
                    for (int j = 0; j < 4; j++) {
                        mma_bf16(acc[j], P, 0u, S, P, bq[2 * j], bq[2 * j + 1]);
                        mma_bf16_k8(acc[j], 0u, S, bq[8 + j]);
                    }
                } else if (ti == 3)
                    acc[3][3] += __uint_as_float(kk << 16) * (bf2f(*reinterpret_cast<const bf16*>(sm + CV_SM_B + c * BX_LEN + BX_9 + (128 + g) * 2)) + bf2f(Us[c * ULEN + UPADF + (g < 3 ? -32 : g - 3)]));
                mbar_wait(cnt + 8 * c, 0);
                uint32_t yw[8];
                ldsm_x4_t(yw, smem_u32(yq) + offc); ldsm_x4_t(yw + 4, smem_u32(yq) + offc + 512);
                TSTAMP(8);
#pragma unroll
                for (int k = 0; k < 2; k++) xv[k] = *reinterpret_cast<const uint4*>(Xs + c * XLEN + 512 * Q + 256 * k + 8 * lane);
#pragma unroll
                for (int k = 0; k < 8; k++) yw[k] = pack2(acc[k >> 1][2 * (k & 1)] + __uint_as_float(yw[k] << 16), acc[k >> 1][2 * (k & 1) + 1] + __uint_as_float(yw[k] & 0xffff0000u));
                stsm_x4_t(smem_u32(yq) + offc, yw[0], yw[1], yw[2], yw[3]);
                stsm_x4_t(smem_u32(yq) + offc + 512, yw[4], yw[5], yw[6], yw[7]);
                __syncwarp();
            } else {
#pragma unroll
                for (int k = 0; k < 2; k++) xv[k] = *reinterpret_cast<const uint4*>(Xs + c * XLEN + 256 * k + 8 * lane);
                mbar_wait(cnt + 8 * c, 0);
            }
#pragma unroll
            for (int k = 0; k < 2; k++) yv[k] = *reinterpret_cast<const uint4*>(yq + 512 * k + usw(lane) * 16);
            if (Q == 0 && lane == 31) {
                const uint32_t b5 = *reinterpret_cast<const uint32_t*>(sm + CV_SM_B + c * BX_LEN + BX_5 + 156);
                yv[1].w = pack2(fmaf(__uint_as_float(kk << 16), __uint_as_float(b5 << 16), __uint_as_float(yv[1].w << 16)),
                                fmaf(__uint_as_float(kk << 16), __uint_as_float(b5 & 0xffff0000u), __uint_as_float(yv[1].w & 0xffff0000u)));
            }
#pragma unroll
            for (int k = 0; k < 2; k++) {
                if (layer)
                    asm volatile("st.relaxed.gpu.global.v4.u32 [%0], {%1,%2,%3,%4};" ::"l"(dst + (size_t)(d0 + c) * XCP + 512 * Q + 256 * k + 8 * lane),
                                 "r"(add2(__byte_perm(xv[k].x, xv[k].z, 0x5410), yv[k].x)), "r"(add2(__byte_perm(xv[k].x, xv[k].z, 0x7632), yv[k].y)),
                                 "r"(add2(__byte_perm(xv[k].y, xv[k].w, 0x5410), yv[k].z)), "r"(add2(__byte_perm(xv[k].y, xv[k].w, 0x7632), yv[k].w)) : "memory");
                else {
                    uint2* dp = reinterpret_cast<uint2*>(dst + (size_t)(d0 + c) * XCP + 512 * Q + 256 * k) + (lane >> 4) * 32 + (lane & 15);
                    dp[0] = make_uint2(add2(xv[k].x, __byte_perm(yv[k].x, yv[k].y, 0x5410)), add2(xv[k].y, __byte_perm(yv[k].z, yv[k].w, 0x5410)));
                    dp[16] = make_uint2(add2(xv[k].z, __byte_perm(yv[k].x, yv[k].y, 0x7632)), add2(xv[k].w, __byte_perm(yv[k].z, yv[k].w, 0x7632)));
                }
            }
        }
        TSTAMP(4);
        if (layer == 1) {
            const int mb = blockIdx.x >> 3, cg = blockIdx.x & 7;
            const bf16* src = dst + (size_t)(cg * 80 + (tid >> 4)) * XCP + mb * 128 + (tid & 15) * 8;
            uint32_t v[3][4];
            __syncthreads();
            uint32_t todo = warp < 8 ? 7 : 3;
#pragma unroll 1
            for (int it = 0; it < SPIN_MAX; it++) {
#pragma unroll
                for (int k = 0; k < 3; k++)
                    if (todo >> k & 1)
                        asm volatile("ld.relaxed.gpu.global.v4.u32 {%0,%1,%2,%3}, [%4];" : "=r"(v[k][0]), "=r"(v[k][1]), "=r"(v[k][2]), "=r"(v[k][3]) : "l"(src + k * (32 * XCP)) : "memory");
#pragma unroll
                for (int k = 0; k < 3; k++)
                    if ((todo >> k & 1) && v[k][0] != ~0u && v[k][1] != ~0u && v[k][2] != ~0u && v[k][3] != ~0u) {
                        *reinterpret_cast<uint4*>(sm + (32 * k + (tid >> 4)) * 272 + (tid & 15) * 16) = make_uint4(v[k][0], v[k][1], v[k][2], v[k][3]);
                        todo ^= 1u << k;
                    }
                if (!todo) break;
                __nanosleep(CV_SLEEP);
            }
            __syncthreads();
            uint32_t w[12];
#pragma unroll
            for (int k = 0; k < 3; k++) ldsm_x4(&w[4 * k], smem_u32(sm) + min(32 * k + lane, 79) * 272 + warp * 16);
            const uint32_t ot = smem_u32(sm + CV_SM_O) + warp * 1280, oa = ot + (lane & 7) * 160 + (lane >> 3) * 16;
            stsm_x4_t(oa, w[0], w[1], w[2], w[3]);
            stsm_x4_t(oa + 64, w[4], w[5], w[6], w[7]);
            asm volatile("stmatrix.sync.aligned.m8n8.x2.trans.shared.b16 [%0], {%1,%2};" ::"r"(oa + 128), "r"(w[8]), "r"(w[9]) : "memory");
            fence_async_smem();
            __syncwarp();
            if (lane == 0) tma_store_2d(&tmOut, cg * 80, mb * 128 + 8 * warp, ot);
        }
    }
    TSTAMP(3);
    GSTAMP(g_tim, 14);
    SPAN(3 + 4 * layer, 3);
}

template <int TA, int TB>
__device__ __forceinline__ void wgmma_n240(float (&d)[120], uint64_t da, uint64_t db, int acc) {
    asm volatile("{\n.reg .pred p;\nsetp.ne.b32 p, %124, 0;\nwgmma.mma_async.sync.aligned.m64n240k16.f32.bf16.bf16 {%0,%1,%2,%3,%4,%5,%6,%7,%8,%9,%10,%11,%12,%13,%14,%15,%16,%17,%18,%19,%20,%21,%22,%23,%24,%25,%26,%27,%28,%29,%30,%31,%32,%33,%34,%35,%36,%37,%38,%39,%40,%41,%42,%43,%44,%45,%46,%47,%48,%49,%50,%51,%52,%53,%54,%55,%56,%57,%58,%59,%60,%61,%62,%63,%64,%65,%66,%67,%68,%69,%70,%71,%72,%73,%74,%75,%76,%77,%78,%79,%80,%81,%82,%83,%84,%85,%86,%87,%88,%89,%90,%91,%92,%93,%94,%95,%96,%97,%98,%99,%100,%101,%102,%103,%104,%105,%106,%107,%108,%109,%110,%111,%112,%113,%114,%115,%116,%117,%118,%119}, %120, %121, p, 1, 1, %122, %123;\n}"
                 : "+f"(d[0]), "+f"(d[1]), "+f"(d[2]), "+f"(d[3]), "+f"(d[4]), "+f"(d[5]), "+f"(d[6]), "+f"(d[7]), "+f"(d[8]), "+f"(d[9]), "+f"(d[10]), "+f"(d[11]), "+f"(d[12]), "+f"(d[13]), "+f"(d[14]), "+f"(d[15]), "+f"(d[16]), "+f"(d[17]), "+f"(d[18]), "+f"(d[19]), "+f"(d[20]), "+f"(d[21]), "+f"(d[22]), "+f"(d[23]), "+f"(d[24]), "+f"(d[25]), "+f"(d[26]), "+f"(d[27]), "+f"(d[28]), "+f"(d[29]), "+f"(d[30]), "+f"(d[31]), "+f"(d[32]), "+f"(d[33]), "+f"(d[34]), "+f"(d[35]), "+f"(d[36]), "+f"(d[37]), "+f"(d[38]), "+f"(d[39]), "+f"(d[40]), "+f"(d[41]), "+f"(d[42]), "+f"(d[43]), "+f"(d[44]), "+f"(d[45]), "+f"(d[46]), "+f"(d[47]), "+f"(d[48]), "+f"(d[49]), "+f"(d[50]), "+f"(d[51]), "+f"(d[52]), "+f"(d[53]), "+f"(d[54]), "+f"(d[55]), "+f"(d[56]), "+f"(d[57]), "+f"(d[58]), "+f"(d[59]), "+f"(d[60]), "+f"(d[61]), "+f"(d[62]), "+f"(d[63]), "+f"(d[64]), "+f"(d[65]), "+f"(d[66]), "+f"(d[67]), "+f"(d[68]), "+f"(d[69]), "+f"(d[70]), "+f"(d[71]), "+f"(d[72]), "+f"(d[73]), "+f"(d[74]), "+f"(d[75]), "+f"(d[76]), "+f"(d[77]), "+f"(d[78]), "+f"(d[79]), "+f"(d[80]), "+f"(d[81]), "+f"(d[82]), "+f"(d[83]), "+f"(d[84]), "+f"(d[85]), "+f"(d[86]), "+f"(d[87]), "+f"(d[88]), "+f"(d[89]), "+f"(d[90]), "+f"(d[91]), "+f"(d[92]), "+f"(d[93]), "+f"(d[94]), "+f"(d[95]), "+f"(d[96]), "+f"(d[97]), "+f"(d[98]), "+f"(d[99]), "+f"(d[100]), "+f"(d[101]), "+f"(d[102]), "+f"(d[103]), "+f"(d[104]), "+f"(d[105]), "+f"(d[106]), "+f"(d[107]), "+f"(d[108]), "+f"(d[109]), "+f"(d[110]), "+f"(d[111]), "+f"(d[112]), "+f"(d[113]), "+f"(d[114]), "+f"(d[115]), "+f"(d[116]), "+f"(d[117]), "+f"(d[118]), "+f"(d[119])
                 : "l"(da), "l"(db), "n"(TA), "n"(TB), "r"(acc));
}

__device__ __forceinline__ void wgmma_n80(float (&d)[40], uint64_t da, uint64_t db, int acc) {
    asm volatile("{\n.reg .pred p;\nsetp.ne.b32 p, %42, 0;\nwgmma.mma_async.sync.aligned.m64n80k16.f32.bf16.bf16 {%0,%1,%2,%3,%4,%5,%6,%7,%8,%9,%10,%11,%12,%13,%14,%15,%16,%17,%18,%19,%20,%21,%22,%23,%24,%25,%26,%27,%28,%29,%30,%31,%32,%33,%34,%35,%36,%37,%38,%39}, %40, %41, p, 1, 1, 0, 1;\n}"
                 : "+f"(d[0]), "+f"(d[1]), "+f"(d[2]), "+f"(d[3]), "+f"(d[4]), "+f"(d[5]), "+f"(d[6]), "+f"(d[7]), "+f"(d[8]), "+f"(d[9]), "+f"(d[10]), "+f"(d[11]), "+f"(d[12]), "+f"(d[13]), "+f"(d[14]), "+f"(d[15]), "+f"(d[16]), "+f"(d[17]), "+f"(d[18]), "+f"(d[19]), "+f"(d[20]), "+f"(d[21]), "+f"(d[22]), "+f"(d[23]), "+f"(d[24]), "+f"(d[25]), "+f"(d[26]), "+f"(d[27]), "+f"(d[28]), "+f"(d[29]), "+f"(d[30]), "+f"(d[31]), "+f"(d[32]), "+f"(d[33]), "+f"(d[34]), "+f"(d[35]), "+f"(d[36]), "+f"(d[37]), "+f"(d[38]), "+f"(d[39])
                 : "l"(da), "l"(db), "r"(acc));
}

constexpr int A1_THREADS = 384;
constexpr int A1_NST = 4;
#define A1_SKEW 8
constexpr int A1_STAGE = 16384 + WQ_STAGE;
constexpr int A1_KVP = 336;
constexpr int A1_SM_KV = 2 * A1_STAGE;
constexpr int A1_SM_BAR = A1_NST * A1_STAGE;
constexpr int A1_SM_RS = A1_SM_BAR + 512;
constexpr int A1_SM_W0 = A1_SM_BAR + 3072, A1_SM_W3 = A1_SM_BAR - 3 * WOB, A1_SM_A1 = 2 * WOB, A1_SM_A0 = A1_SM_A1 + 61440;
constexpr int A1_SM_XA = A1_SM_W0 + 2 * WOB, A1_SM_XB = A1_SM_XA + 2048;
constexpr int A1_SMEM = A1_SM_W0 + 3 * WOB;
static_assert(A1_SM_W3 >= A1_SM_KV + 144 * A1_KVP && A1_SM_W3 % 512 == 0 && A1_SM_A1 % 1024 == 0 && A1_SM_A0 <= A1_SM_KV && A1_SM_A0 + 61440 <= A1_SM_W3 && A1_SMEM <= 232448, "layout");
__device__ __forceinline__ constexpr uint32_t wo_off(int h) { return h * WOB + (h < 3 ? A1_SM_W0 : h < 6 ? A1_SM_W3 - 3 * WOB : -6 * WOB); }
#define A1_FRED "red.relaxed.gpu.global.add.u32"
#define A1_FLD "ld.acquire.gpu.global.u32"
#define ST_SLEEP 20
#define ST_SLEEP0 300
#define WO_LATE bar_done
#define A1_P0 2
#define A1_PW (kb - 2)
#define A1_FSPIN SPIN_MAX
#define A1_FSLEEP 40
#define A1_WOAT 6

template <int L>
__device__ __forceinline__ void a1_mainloop(float (&acc)[120], uint32_t sbase, uint32_t bars, int wg, int tile) {
    constexpr int layer = L; (void)layer;
    const uint64_t da0 = L ? make_desc(sbase + wg * 8192, 8192, 1024, 1) : make_desc(sbase + wg * 8192, 16, 1024, 1), db0 = make_desc(sbase + 16384, 1024, 256, 3);
#pragma unroll 1
    for (int t = 0;; t++) {
        const int st = t % A1_NST;
        mbar_wait(bars + 8 * st, (t / A1_NST) & 1);
        if (t == A1_SKEW && wg == 0) mbar_wait(bars + 160, 0);
        TSTAMP3(1 + t);
        wgmma_fence();
#pragma unroll
        for (int kk = 0; kk < 4; kk++) wgmma_n240<L, 1>(acc, da0 + (uint32_t)(st * (A1_STAGE / 16) + kk * (L ? 128 : 2)), db0 + (uint32_t)(st * (A1_STAGE / 16) + (kk >> 1) * (WQ_STAGE / 32) + (kk & 1) * 32), kk ? 1 : t);
        wgmma_commit();
        if (t == 9) break;
        if (t == A1_SKEW - 1 && wg == 0) wgmma_wait<0>(); else wgmma_wait<1>();
        if (t > 0 && (threadIdx.x & 127) == 0) {
            if (t != A1_SKEW || wg) mbar_arrive(bars + 8 * (A1_NST + (t - 1) % A1_NST));
            if (t == A1_SKEW - 1 && wg == 0) mbar_arrive(bars + 8 * (A1_NST + t % A1_NST));
        }
    }
}

__global__ void __launch_bounds__(A1_THREADS, 1) a1_kernel(const int layer, const bf16* __restrict__ x0, const unsigned char* __restrict__ wq, const unsigned char* __restrict__ wo,
                                                           float2* __restrict__ rsum, uint4* __restrict__ of, const __grid_constant__ CUtensorMap tmX,
                                                           const __grid_constant__ CUtensorMap tmR, const __grid_constant__ CUtensorMap tmX1, const __grid_constant__ TileTab tab) {
    extern __shared__ __align__(1024) unsigned char stg[];
    const uint32_t sbase = smem_u32(stg);
    const uint32_t bars = sbase + A1_SM_BAR;
    const uint32_t bar_stat = bars + 64, bar_kv = bars + 72, bar_rd = bars + 168;
    const uint32_t bar_wo = bars + 208, bar_done = bars + 216, bar_pv = bars + 224, bar_kvf = bars + 232, bar_f2 = bars + 248, bar_e2 = bars + 384, que = bars + 448;
    const int tid = threadIdx.x;
    const int w = __shfl_sync(~0u, tid >> 5, 0), wg = w >> 2;
    uint32_t smid, ns;
    asm volatile("mov.u32 %0, %smid;" : "=r"(smid));
    asm volatile("mov.u32 %0, %nsmid;" : "=r"(ns));
    const auto te = tab.e[ns == tab.ns ? smid : 132 + blockIdx.x];
    const int tile = te.tile, mb = te.mb, hg = te.hg;
    float2* rst = reinterpret_cast<float2*>(stg + A1_SM_RS) + 8;
    auto issue_w = [&](int it) { bulk_load(sbase + (it % A1_NST) * A1_STAGE + 16384, wq + te.woff + it * WQ_STAGE, WQ_STAGE, bars + 8 * (it % A1_NST)); };
    auto issue_x = [&](int it, int kb) {
        asm volatile("cp.async.bulk.tensor.5d.shared::cluster.global.mbarrier::complete_tx::bytes [%0], [%1, {%3, %3, %3, %4, %5}], [%2];"
                     ::"r"(sbase + (it % A1_NST) * A1_STAGE), "l"(&tmX), "r"(bars + 8 * (it % A1_NST)), "r"(0), "r"(mb), "r"(kb) : "memory");
    };
    if (w == 8 && tile < 128) {
        const bool one = elect();
        if (one) {
#pragma unroll
            for (int i = 0; i < A1_NST; i++) mbar_init(bars + 8 * i, 1);
            asm volatile("fence.mbarrier_init.release.cluster;" ::: "memory");
        }
        __syncwarp();
        asm volatile("bar.arrive 0, 384;" ::: "memory");
        if (one) {
#define PW asm volatile("griddepcontrol.wait;" ::: "memory");
            if (layer) { issue_w(0); PW issue_x(0, te.kb0); issue_x(1, te.kb0 + 1); }
            else { issue_x(0, te.kb0); issue_x(1, te.kb0 + 1); PW issue_w(0); }
            issue_w(1);
#pragma unroll
            for (int i = 0; i < A1_NST; i++) mbar_expect_tx(bars + 8 * i, A1_STAGE);
            asm volatile("griddepcontrol.launch_dependents;" ::: "memory");
#pragma unroll
            for (int kb = 2; kb < A1_P0; kb++) { issue_x(kb, te.kb0 + kb); issue_w(kb); }
            DBGC(34); DBGV(33, smid); DBGV(40, t_entry); DBGV(30, t_a); DBGV(31, t_b); DBGV(32, t_c); DBGV(38, t_d); DBGV(39, t_e);
        }
    }
    if (tile >= 128) { sm_idle(layer); return; }
    if (wg == 2) {
        if (w != 8) {
            if (tid == 320) { prefetch_tmap(&tmX); prefetch_tmap(&tmR); prefetch_tmap(&tmX1); }
            asm volatile("bar.sync 0, 384;" ::: "memory");
        }
        if (w == 9) {
            asm volatile("bar.arrive 3, 64;" ::: "memory");
            if (layer == 0) pdl_sync();
            float4 a[2] = {};
#pragma unroll
            for (int k = 0; k < 10; k++)
#pragma unroll
                for (int h = 0; h < 2; h++) {
                    const int c4 = min(tid - 288 + 32 * h, 59);
                    const float4 v = __ldcg(reinterpret_cast<const float4*>(g_csp + k * 1920 + hg * 80) + c4 + (c4 / 20) * 140);
                    a[h].x += v.x; a[h].y += v.y; a[h].z += v.z; a[h].w += v.w;
                }
#pragma unroll
            for (int h = 0; h < 2; h++)
#pragma unroll
                for (int k = 0; k < 4; k++) {
                    const float c = 0.5f * (k == 0 ? a[h].x : k == 1 ? a[h].y : k == 2 ? a[h].z : a[h].w), c1 = c - rbf(c), c2 = c1 - rbf(c1);
                    *reinterpret_cast<uint4*>(stg + A1_SM_XB + (4 * min(tid - 288 + 32 * h, 59) + k) * 16) = make_uint4(pack2(c, c1), pack2(c2, 0.f), 0u, 0u);
                }
            fence_async_smem();
            __syncwarp();
            if (tid == 288) mbar_arrive(bar_stat);
#pragma unroll 4
            for (int k = 0; k < 40; k++) asm volatile("st.global.v4.u32 [%0], {%1,%1,%1,%1};" ::"l"(of + (mb * 8 + hg) * 1280 + 32 * k + (tid - 288)), "r"(~0u) : "memory");
            asm volatile("fence.acq_rel.gpu;" ::: "memory");
            asm volatile("fence.proxy.async.global;" ::: "memory");
            __syncwarp();
            if (tid == 288) mbar_arrive(bar_done);
            TSTAMP1T(9, 288);
        } else if (w == 8) {
            asm volatile("bar.sync 3, 64;" ::: "memory");
            if (elect()) {
#pragma unroll 1
                for (int kb = A1_P0; kb < 10; kb++) {
                    if (kb < A1_NST) mbar_wait(bars + 8 * A1_PW, 0);
                    else {
                        mbar_wait(bars + 8 * (A1_NST + kb % A1_NST), ((kb / A1_NST) - 1) & 1);
                        if (layer && kb < 9) mbar_wait(bar_rd + 8 * (kb - A1_NST), 0);
                        mbar_expect_tx(bars + 8 * (kb % A1_NST), A1_STAGE);
                    }
                    issue_x(kb, kb < 5 ? kb + te.kb0 : kb - te.kb0); issue_w(kb);
                    if (kb == A1_WOAT) {
                        mbar_expect_tx(bar_wo, 8 * WOB);
                        bulk_load(sbase + A1_SM_W0, wo + hg * 8 * WOB, 2 * WOB, bar_wo);
                    }
                }
                TSTAMP1T(6, 256);
                mbar_wait(bars + 8 * (A1_NST + 3), 1);
                bulk_load(sbase + A1_SM_W3, wo + (hg * 8 + 3) * WOB, 3 * WOB, bar_wo);
            }
            __syncwarp();
        } else {
            const int j = tid - 320;
            const uint32_t tag = ld_epoch();
            if (tid == 352) sm_started(layer);
            if (layer == 0) {
                const uint4* src = reinterpret_cast<const uint4*>(x0 + (size_t)(mb * 128 + hg * 16 + (j >> 2)) * DM);
                uint4 v[20];
#pragma unroll
                for (int k = 0; k < 20; k++) v[k] = __ldg(src + (j & 3) + 4 * k);
                const float p0 = __uint_as_float(__shfl_sync(~0u, v[0].x, j & 28) << 16);
                float s[2] = {0.f, 0.f}, q[2] = {0.f, 0.f};
#pragma unroll
                for (int k = 0; k < 20; k++) {
                    const uint32_t w[4] = {v[k].x, v[k].y, v[k].z, v[k].w};
#pragma unroll
                    for (int i = 0; i < 4; i++) {
                        const float a = __uint_as_float(w[i] << 16) - p0, b = __uint_as_float(w[i] & 0xffff0000u) - p0;
                        s[0] += a; s[1] += b; q[0] = fmaf(a, a, q[0]); q[1] = fmaf(b, b, q[1]);
                    }
                }
                float s0 = s[0] + s[1], q0 = q[0] + q[1];
#pragma unroll
                for (int o = 1; o <= 2; o <<= 1) { s0 += __shfl_xor_sync(~0u, s0, o); q0 += __shfl_xor_sync(~0u, q0, o); }
                if ((j & 3) == 0) {
                    const float d = s0 * (1.0f / DM);
                    const uint32_t ms = pack2(p0 + d, sqrt_apx(rbf(rbf(fmaxf(fmaf(-d, d, q0 * (1.0f / DM)), 0.f)) + 1e-5f)));
                    asm volatile("st.global.cg.u64 [%0], %1;" ::"l"(g_rstat + mb * 128 + (j & 4) * 16 + hg * 8 + (j >> 3)), "l"(tagw(ms, tag)) : "memory");
                    g_piv[mb * 128 + hg * 16 + ((j >> 2) & 8) + (j & 4) + ((j >> 3) & 3)] = __ushort_as_bfloat16((unsigned short)ms);
                }
            }
            float o[4];
            int row;
            if (layer == 0) {
                ulonglong2 v;
#pragma unroll 1
                for (int it = 0; it < SPIN_MAX; it++) {
                    v = ld_tag2(reinterpret_cast<const ulonglong2*>(g_rstat + mb * 128) + j);
                    if (tag_ok(v, tag)) break;
                    __nanosleep(100);
                }
                o[0] = __uint_as_float((uint32_t)v.x << 16); o[1] = rcp_apx(__uint_as_float((uint32_t)v.x & 0xffff0000u));
                o[2] = __uint_as_float((uint32_t)v.y << 16); o[3] = rcp_apx(__uint_as_float((uint32_t)v.y & 0xffff0000u));
                row = 2 * j;
            } else {
                const int ch = j & 7, kg = (j >> 3) & 3;
                const unsigned char* src = stg + (j >> 5) * 8192 + (hg & 3) * 2048;
                float s[8], q[8], p0[8];
#pragma unroll
                for (int i = 0; i < 8; i++) { s[i] = 0.f; q[i] = 0.f; }
#pragma unroll 1
                for (int it = 0; it < 5; it++) {
                    uint4 v[4];
                    mbar_wait(bars + 8 * (it % A1_NST), it / A1_NST);
#pragma unroll
                    for (int k = 0; k < 4; k++) v[k] = *reinterpret_cast<const uint4*>(src + (it % A1_NST) * A1_STAGE + (4 * k + kg) * 128 + ((ch ^ ((4 * k + kg) & 7)) << 4));
                    if (it == 0) {
                        const uint4 pv = *reinterpret_cast<const uint4*>(src + (ch << 4));
                        const uint32_t w[4] = {pv.x, pv.y, pv.z, pv.w};
#pragma unroll
                        for (int i = 0; i < 4; i++) { p0[2 * i] = __uint_as_float(w[i] << 16); p0[2 * i + 1] = __uint_as_float(w[i] & 0xffff0000u); }
                    }
                    asm volatile("" :: "r"(v[0].x), "r"(v[1].x), "r"(v[2].x), "r"(v[3].x), "f"(p0[0]) : "memory");
                    __syncwarp();
                    if ((tid & 31) == 0) mbar_arrive(bar_rd + 8 * it);
#pragma unroll
                    for (int k = 0; k < 4; k++) {
                        const uint32_t w[4] = {v[k].x, v[k].y, v[k].z, v[k].w};
#pragma unroll
                        for (int i = 0; i < 4; i++) {
                            const float a = __uint_as_float(w[i] << 16) - p0[2 * i], b = __uint_as_float(w[i] & 0xffff0000u) - p0[2 * i + 1];
                            s[2 * i] += a; s[2 * i + 1] += b; q[2 * i] = fmaf(a, a, q[2 * i]); q[2 * i + 1] = fmaf(b, b, q[2 * i + 1]);
                        }
                    }
                }
#pragma unroll
                for (int i = 0; i < 4; i++) {
                    const bool up = kg & 2;
                    const float ss = __shfl_xor_sync(~0u, up ? s[i] : s[i + 4], 16), qq = __shfl_xor_sync(~0u, up ? q[i] : q[i + 4], 16);
                    s[i] = (up ? s[i + 4] : s[i]) + ss; q[i] = (up ? q[i + 4] : q[i]) + qq; p0[i] = up ? p0[i + 4] : p0[i];
                }
#pragma unroll
                for (int i = 0; i < 2; i++) {
                    const bool up = kg & 1;
                    const float ss = __shfl_xor_sync(~0u, up ? s[i] : s[i + 2], 8), qq = __shfl_xor_sync(~0u, up ? q[i] : q[i + 2], 8);
                    s[i] = (up ? s[i + 2] : s[i]) + ss; q[i] = (up ? q[i + 2] : q[i]) + qq; p0[i] = up ? p0[i + 2] : p0[i];
                }
                uint4* gp = g_halo + 86016 + mb * 512 + j;
                const float d0 = s[0] * (1.0f / 80.0f), d1 = s[1] * (1.0f / 80.0f);
                asm volatile("st.relaxed.gpu.global.v4.f32 [%0], {%1,%2,%3,%4};" ::"l"(gp + hg * 64), "f"(p0[0] + d0), "f"(fmaxf(fmaf(-d0, s[0], q[0]), 0.f)), "f"(p0[1] + d1), "f"(fmaxf(fmaf(-d1, s[1], q[1]), 0.f)) : "memory");
                __nanosleep(ST_SLEEP0);
                uint32_t pw[8][4], todo = 0xff;
#pragma unroll 1
                for (int it = 0; it < SPIN_MAX; it++) {
#pragma unroll
                    for (int k = 0; k < 8; k++)
                        if (todo >> k & 1) asm volatile("ld.relaxed.gpu.global.v4.u32 {%0,%1,%2,%3}, [%4];" : "=r"(pw[k][0]), "=r"(pw[k][1]), "=r"(pw[k][2]), "=r"(pw[k][3]) : "l"(gp + k * 64) : "memory");
#pragma unroll
                    for (int k = 0; k < 8; k++)
                        if (__all_sync(~0u, pw[k][0] != ~0u && pw[k][1] != ~0u && pw[k][2] != ~0u && pw[k][3] != ~0u)) todo &= ~(1u << k);
                    if (!todo) break;
                    __nanosleep(ST_SLEEP);
                }
#pragma unroll
                for (int r = 0; r < 2; r++) {
                    float mean = 0.f, m2 = 0.f;
#pragma unroll
                    for (int k = 0; k < 8; k++) mean += __uint_as_float(pw[k][2 * r]);
                    mean *= 0.125f;
#pragma unroll
                    for (int k = 0; k < 8; k++) {
                        const float dm = __uint_as_float(pw[k][2 * r]) - mean;
                        m2 += fmaf(80.0f * dm, dm, __uint_as_float(pw[k][2 * r + 1]));
                    }
                    o[2 * r] = rbf(mean);
                    o[2 * r + 1] = rcp_apx(rbf(sqrt_apx(rbf(rbf(m2 * (1.0f / DM)) + 1e-5f))));
                }
                row = (j >> 5) * 64 + (j & 7) * 8 + ((j >> 3) & 3) * 2;
                if (hg == 0) *reinterpret_cast<uint32_t*>(g_piv + SEQ + mb * 128 + 2 * (row & 60) + 4 * (row >> 6) + (row & 3)) = __byte_perm(__float_as_uint(o[0]), __float_as_uint(o[2]), 0x7632);
            }
#pragma unroll
            for (int r = 0; r < 2; r++)
                *reinterpret_cast<uint4*>(stg + A1_SM_XA + (row + r) * 16) = make_uint4(__byte_perm(__float_as_uint(-o[2 * r]), 0, 0x3232), __float_as_uint(-o[2 * r]) >> 16, 0u, 0u);
            *reinterpret_cast<float4*>(rst + row + (row >> 6) * 8) = make_float4(o[0], o[1], o[2], o[3]);
            fence_async_smem();
            TSTAMP1T(7, 320);
            if (tid == 320) DBGC(44);
            __syncwarp();
            if ((tid & 31) == 0) mbar_arrive(bar_stat);
        }
        if (tid == 320) DBGCAL(0);
        if (tid == 352) {
            mbar_wait(WO_LATE, 0);
            mbar_wait(bar_done, 0);
            bulk_load(sbase, wo + (hg * 8 + 6) * WOB, 2 * WOB, bar_wo);
            bulk_load(sbase + A1_SM_W0 + 2 * WOB, wo + (hg * 8 + 2) * WOB, WOB, bar_wo);
        }
        if (w < 10) {
            const int cw = w - 8;
            const uint32_t* fl = reinterpret_cast<const uint32_t*>(rsum + 2 * SEQ) + (((layer * 16 + mb) * 2 + cw) * 8 + (tid & 7)) * FSTR;
            const unsigned char* src = reinterpret_cast<const unsigned char*>(of) + mb * 163840 + cw * 10240 + (tid & 7) * 20480;
            const uint32_t sl = sbase + (cw ? A1_SM_A1 : A1_SM_A0);
            mbar_wait(cw ? bar_done : bar_kvf, 0);
            if ((tid & 31) == 0) {
                mbar_expect_tx(bar_f2 + 64 * cw + 64, 10240);
                tma_load_3d(sl + 51200, &tmR, layer ? 0 : hg * 80, layer ? hg * 80 : mb * 64, layer ? mb * 2 + cw : cw, bar_f2 + 64 * cw + 64);
            }
            __syncwarp();
            uint32_t pend = 0xffu & ~(1u << hg), v = 0;
            const uint32_t bo = wo_off((tid & 7) + ((tid & 7) < hg)) >> 4, lt = (1u << (tid & 31)) - 1;
#pragma unroll 1
            for (int it = 0; pend && it < 2 * SPIN_MAX; it++) {
                if (v != 4 && (pend >> (tid & 31) & 1)) asm volatile(A1_FLD " %0, [%1];" : "=r"(v) : "l"(fl) : "memory");
                uint32_t fr;
                asm volatile("{\n.reg .pred p;\nmbarrier.test_wait.parity.shared::cta.b64 p, [%1], 0;\nselp.b32 %0, 1, 0, p;\n}" : "=r"(fr) : "r"(bar_e2 + 16 * cw + (tid & 1) * 8) : "memory");
                fr = __ballot_sync(~0u, fr);
                uint32_t m = __ballot_sync(~0u, v == 4 || it >= A1_FSPIN) & pend;
                const int q = 8 - __popc(pend) + __popc(m & lt);
                m &= __ballot_sync(~0u, q < ((fr & 2) ? 8 : (fr & 1) ? 7 : 5));
                pend ^= m;
                if (m >> (tid & 31) & 1) DBGC(12 + cw * 8 + (tid & 7));
                if (!m) __nanosleep(A1_FSLEEP);
                else asm volatile("fence.proxy.async.global;" ::: "memory");
                if (m >> (tid & 31) & 1) {
                    bulk_load(q == 7 && !cw ? sbase + A1_SM_W0 : sl + (q < 6 ? q : q - 6) * 10240, src, 10240, bar_f2 + 64 * cw + 8 * q);
                    asm volatile("st.shared.u32 [%0], %1;" ::"r"(que + 32 * cw + 4 * q), "r"(bo) : "memory");
                    mbar_expect_tx(bar_f2 + 64 * cw + 8 * q, 10240);
                    DBGC(44 + cw * 8 + q);
                }
                __syncwarp();
            }
        }
    } else {
        if (tid == 0) {
            mbar_init(bar_stat, 3);
#pragma unroll
            for (int i = 0; i < 8; i++) mbar_init(bar_kv + 8 * i, 1);
            mbar_init(bars + 144, 1);
            mbar_init(bars + 160, 1);
#pragma unroll
            for (int i = 0; i < 5; i++) mbar_init(bar_rd + 8 * i, 2);
            asm volatile("fence.mbarrier_init.release.cluster;" ::: "memory");
        } else if (tid == 32) {
            mbar_init(bar_wo, 1); mbar_init(bar_done, 3); mbar_init(bar_pv, 4); mbar_init(bar_kvf, 8); mbar_init(bars + 240, 4);
#pragma unroll
            for (int i = 0; i < 4; i++) { mbar_init(bar_e2 + 8 * i, i == 1 ? 2 : 1); mbar_init(bars + 8 * (A1_NST + i), 2); }
            asm volatile("fence.mbarrier_init.release.cluster;" ::: "memory");
        } else if (tid == 64) {
#pragma unroll
            for (int i = 1; i <= 16; i++) mbar_init(bar_f2 + 8 * i, 1);
            asm volatile("fence.mbarrier_init.release.cluster;" ::: "memory");
        }
        asm volatile("bar.sync 0, 384;" ::: "memory");
        SPAN(1 + 4 * layer, 0);
        constexpr int on = 1;
        float acc[120];
        const int lane = tid & 31, warp = w & 7, g = lane >> 2, t = lane & 3;
        if (on) {
            SPAN(1 + 4 * layer, 1);
            TSTAMP1(0);
            if (threadIdx.x == 0) { GSTAMP(g_tim1, 15); }
            TSTAMP3(0);
            if (tid == 0) TSTAMP2(0);
            TSTAMP4(0);
            if (tid == 0) DBGC(60);
            if (layer == 0) a1_mainloop<0>(acc, sbase, bars, wg, tile); else a1_mainloop<1>(acc, sbase, bars, wg, tile);
            uint32_t ok;
            asm volatile("{\n.reg .pred p;\nmbarrier.test_wait.parity.shared::cta.b64 p, [%1], 0;\nselp.b32 %0, 1, 0, p;\n}" : "=r"(ok) : "r"(bar_stat) : "memory");
            if (tid == 128 && !ok) mbar_arrive(bars + 160);
            __syncwarp();
            mbar_wait(bar_stat, 0);
            wgmma_fence();
            wgmma_n240<0, 0>(acc, make_desc(sbase + A1_SM_XA + wg * 1024, 0, 128, 0), make_desc(sbase + A1_SM_XB, 0, 128, 0), 1);
            wgmma_commit();
            if (tid == 128 && ok) mbar_arrive(bars + 160);
            mbar_wait(bars + 8 * (A1_NST + 3), 1);
        }
        const float2* rw = rst + 16 * warp + 8 * wg;
        const float rb0 = rw[g + 8].y, ra = rw[g].y * 0.22360679774997896f, rb = rb0 * 0.22360679774997896f;
        wgmma_wait<0>();
        if ((tid & 127) == 0) mbar_arrive(bar_done);
        TSTAMP1(2);
        TSTAMP1T(13, 224);
        if ((tid & 127) == 0) DBGC(62 - wg);
        uint32_t f[2][30];
#pragma unroll
        for (int j = 10; j < 30; j++) f[1][j] = pack2(acc[4 * j + 2], acc[4 * j + 3]);
        if ((warp & 3) == 3) {
            uint4* hout = g_halo + (((layer * 16 + mb) * 8 + hg) * 2 + wg) * 168;
#pragma unroll
            for (int j = 0; j < 20; j += 4)
                asm volatile("st.relaxed.gpu.global.v4.u32 [%0], {%1,%2,%3,%4};" ::"l"(hout + 8 * j + lane), "r"(f[1][10 + j]), "r"(f[1][11 + j]), "r"(f[1][12 + j]), "r"(f[1][13 + j]) : "memory");
            if (t == 0) asm volatile("st.relaxed.gpu.global.f32 [%0], %1;" ::"l"(reinterpret_cast<float*>(hout + 160) + g), "f"(rb0) : "memory");
        }
        TSTAMP1T(12, 224);
        const uint32_t kvw = sbase + A1_SM_KV + (16 * warp + 8 * wg) * A1_KVP;
        const uint32_t mrow = kvw + (lane & 7) * A1_KVP + (lane >> 3) * 16;
#pragma unroll
        for (int j = 0; j < 20; j += 4) stsm_x4(mrow + 16 * A1_KVP + 16 * j, f[1][10 + j], f[1][11 + j], f[1][12 + j], f[1][13 + j]);
        __syncwarp();
        if (lane == 0 && (warp & 3) != 3) mbar_arrive(bar_kv + 8 * (warp + 1));
#pragma unroll
        for (int j = 0; j < 30; j++) f[0][j] = pack2(acc[4 * j], acc[4 * j + 1]);
        stsm_x4(mrow + 8 * A1_KVP + 160, f[0][20], f[0][21], f[0][22], f[0][23]);
        stsm_x4(mrow + 8 * A1_KVP + 224, f[0][24], f[0][25], f[0][26], f[0][27]);
        asm volatile("stmatrix.sync.aligned.m8n8.x2.shared.b16 [%0], {%1,%2};" ::"r"(mrow + 8 * A1_KVP + 288), "r"(f[0][28]), "r"(f[0][29]) : "memory");
#pragma unroll
        for (int j = 0; j < 10; j++) f[1][j] = pack2(acc[4 * j + 2], acc[4 * j + 3]);
        __syncwarp();
        uint32_t vb[10][2], vp[12], kp[12];
#pragma unroll
        for (int j = 0; j < 10; j += 2) ldsm_x4_t(&vb[j][0], kvw + (8 + (lane & 15)) * A1_KVP + 160 + (lane >> 4) * 16 + 16 * j);
        const bool up0 = 2 * t > g, up1 = 2 * t + 1 > g, edge = (mb | (warp & 3)) == 0;
        float rk[4];
        auto above = [&]() {
            mbar_wait(bar_kv + 8 * warp, 0);
#pragma unroll
            for (int j = 0; j < 12; j += 4) ldsm_x4(&kp[j], mrow + 16 * j);
            rk[0] = rw[2 * t - (up0 ? 8 : 0)].y; rk[1] = rw[2 * t + 1 - (up1 ? 8 : 0)].y;
#pragma unroll
            for (int j = 0; j < 12; j += 4) ldsm_x4_t(&vp[j], mrow + 160 + 16 * j - (j == 8 ? (lane & 16) * 2 : 0));
            __syncwarp();
            if (lane == 0) mbar_arrive(bar_kvf);
        };
        auto halo = [&]() {
            if (lane == 0) mbar_arrive(bar_kvf);
            const uint4* hin = g_halo + (((layer * 16 + mb - 1) * 8 + hg) * 2 + wg) * 168;
            uint32_t hv[22] = {};
            rk[0] = rw[2 * t].y; rk[1] = rw[2 * t + 1].y;
            if (mb > 0) {
#pragma unroll 1
                for (int it = 0; it < SPIN_MAX; it++) {
#pragma unroll
                    for (int k = 0; k < 20; k += 4)
                        asm volatile("ld.relaxed.gpu.global.v4.u32 {%0,%1,%2,%3}, [%4];" : "=r"(hv[k]), "=r"(hv[k + 1]), "=r"(hv[k + 2]), "=r"(hv[k + 3]) : "l"(hin + 8 * k + lane) : "memory");
                    asm volatile("ld.relaxed.gpu.global.v2.u32 {%0,%1}, [%2];" : "=r"(hv[20]), "=r"(hv[21]) : "l"(reinterpret_cast<const uint2*>(hin + 160) + t) : "memory");
                    uint32_t m = max(hv[20], hv[21]);
#pragma unroll
                    for (int k = 0; k < 20; k += 2) m = __vimax3_u32(m, hv[k], hv[k + 1]);
                    if (!__any_sync(~0u, m == ~0u)) break;
                }
            }
            if (tid == 0) mbar_arrive(bars + 144);
            if (lane == 0) DBGC(52 - 16 * wg);
#pragma unroll
            for (int j = 0; j < 10; j++) {
                kp[j] = hv[j];
                asm volatile("movmatrix.sync.aligned.m8n8.trans.b16 %0, %1;" : "=r"(vp[j]) : "r"(hv[10 + j]));
            }
            if (up0) rk[0] = __uint_as_float(hv[20]);
            if (up1) rk[1] = __uint_as_float(hv[21]);
        };
        rk[2] = rw[2 * t + (up0 ? 0 : 8)].y; rk[3] = rw[2 * t + 1 + (up1 ? 0 : 8)].y;
        uint32_t qs[4][2];
#pragma unroll
        for (int h = 0; h < 4; h++) {
            qs[h][0] = (t >> 1) == (h & 1) ? f[0][5 * (h >> 1) + 2] : 0u; qs[h][1] = (t >> 1) == (h & 1) ? f[1][5 * (h >> 1) + 2] : 0u;
            asm volatile("" : "+r"(qs[h][0]), "+r"(qs[h][1]));
        }
#pragma unroll
        for (int j = 0; j < 10; j++) asm volatile("" : "+r"(f[0][j]), "+r"(f[1][j]), "+r"(f[0][10 + j]));
        if (warp & 3) above(); else if (wg) halo();
        TSTAMP1T(10, 64);
        float sc[4][3][4];
#pragma unroll
        for (int h = 0; h < 4; h++) {
            const int jb = 5 * (h >> 1) + 3 * (h & 1), js = 5 * (h >> 1) + 2;
#pragma unroll
            for (int nt = 1; nt < 3; nt++) {
#pragma unroll
                for (int e = 0; e < 4; e++) sc[h][nt][e] = 0.f;
                mma_bf16(sc[h][nt], f[0][jb], f[1][jb], f[0][jb + 1], f[1][jb + 1], f[nt - 1][10 + jb], f[nt - 1][11 + jb]);
                mma_bf16_k8(sc[h][nt], qs[h][0], qs[h][1], f[nt - 1][10 + js]);
            }
        }
        if (tid == 128) mbar_arrive(bars + 240);
        if (warp == 0) halo();
        TSTAMP1(8);
#pragma unroll
        for (int h = 0; h < 4; h++) {
            const int jb = 5 * (h >> 1) + 3 * (h & 1), js = 5 * (h >> 1) + 2;
#pragma unroll
            for (int e = 0; e < 4; e++) sc[h][0][e] = 0.f;
            mma_bf16(sc[h][0], f[0][jb], f[1][jb], f[0][jb + 1], f[1][jb + 1], kp[jb], kp[jb + 1]);
            mma_bf16_k8(sc[h][0], qs[h][0], qs[h][1], kp[js]);
        }
        if (warp > 4) { __syncwarp(); if (lane == 0) mbar_arrive(bars + 240); }
        TSTAMP1T(3, 64);
        float p[4][4], sum[4][2];
        uint32_t lg[4][2], mx[4];
        const float rl[4] = {rk[0] * ra, rk[1] * ra, rk[2] * rb, rk[3] * rb};
        auto max2 = [](uint32_t a, uint32_t b) { uint32_t r; asm("max.bf16x2 %0, %1, %2;" : "=r"(r) : "r"(a), "r"(b)); return r; };
#pragma unroll
        for (int h = 0; h < 4; h++) {
            lg[h][0] = pack2((up0 ? sc[h][0][0] : sc[h][1][0]) * rl[0], (up0 ? sc[h][1][2] : sc[h][2][2]) * rl[2]);
            lg[h][1] = pack2((up1 ? sc[h][0][1] : sc[h][1][1]) * rl[1], (up1 ? sc[h][1][3] : sc[h][2][3]) * rl[3]);
            if (edge) {
                if (up0) lg[h][0] = __byte_perm(lg[h][0], 0xce6eu, 0x3254);
                if (up1) lg[h][1] = __byte_perm(lg[h][1], 0xce6eu, 0x3254);
            }
            mx[h] = max2(lg[h][0], lg[h][1]);
        }
#pragma unroll
        for (int o = 1; o <= 2; o <<= 1)
#pragma unroll
            for (int h = 0; h < 4; h++) mx[h] = max2(mx[h], __shfl_xor_sync(~0u, mx[h], o));
#pragma unroll
        for (int h = 0; h < 4; h++)
#pragma unroll
            for (int r = 0; r < 2; r++) {
                const float m = __uint_as_float(r ? mx[h] & 0xffff0000u : mx[h] << 16);
#pragma unroll
                for (int e = 0; e < 2; e++)
                    asm("ex2.approx.ftz.f32 %0, %1;" : "=f"(p[h][2 * r + e]) : "f"((__uint_as_float(r ? lg[h][e] & 0xffff0000u : lg[h][e] << 16) - m) * 1.4426950408889634f));
                sum[h][r] = p[h][2 * r] + p[h][2 * r + 1];
            }
#pragma unroll
        for (int o = 1; o <= 2; o <<= 1)
#pragma unroll
            for (int h = 0; h < 4; h++)
#pragma unroll
                for (int r = 0; r < 2; r++) sum[h][r] += __shfl_xor_sync(~0u, sum[h][r], o);
        TSTAMP1T(5, 64);
        const uint32_t mu = (up0 ? 0xffffu : 0u) | (up1 ? 0xffff0000u : 0u);
        uint32_t ob[10][2];
#pragma unroll
        for (int P = 0; P < 2; P++) {
            float os[2][4];
#pragma unroll
            for (int e = 0; e < 2; e++) {
                const int h = 2 * P + e;
                const float i0 = rcp_apx(sum[h][0]), i1 = rcp_apx(sum[h][1]);
                const uint32_t w0 = pack2(p[h][0] * rk[0] * i0, p[h][1] * rk[1] * i0), w1 = pack2(p[h][2] * rk[2] * i1, p[h][3] * rk[3] * i1);
#pragma unroll
                for (int dt = 0; dt < 3; dt++) {
                    const int j = 5 * P + (dt < 2 ? 3 * e + dt : 2);
                    float o[4] = {0.f, 0.f, 0.f, 0.f};
                    mma_bf16(o, w0 & ~mu, w1 & mu, 0u, w1 & ~mu, vb[j][0], vb[j][1]);
                    mma_bf16_k8(o, w0 & mu, 0u, vp[j]);
                    if (dt < 2) { ob[j][0] = pack2(o[0], o[1]); ob[j][1] = pack2(o[2], o[3]); }
                    else { os[e][0] = o[0]; os[e][1] = o[1]; os[e][2] = o[2]; os[e][3] = o[3]; }
                }
            }
#pragma unroll
            for (int k = 0; k < 4; k++) os[0][k] = t < 2 ? os[0][k] : os[1][k];
            ob[5 * P + 2][0] = pack2(os[0][0], os[0][1]); ob[5 * P + 2][1] = pack2(os[0][2], os[0][3]);
        }
        const uint32_t sl = sbase + (wg ? A1_SM_A1 : A1_SM_A0);
        const uint32_t o0 = (warp & 3) * 2048 + g * 64 + ((t ^ (g >> 1)) << 4), o1 = 8192 + (warp & 3) * 512 + g * 32 + ((t ^ ((g >> 2) << 1)) << 3);
        mbar_wait(bar_done, 0);
        if (wg == 0) mbar_wait(bar_kvf, 0);
#pragma unroll
        for (int h = 0; h < 2; h++) {
            asm volatile("st.shared.v4.u32 [%0], {%1,%2,%3,%4};" ::"r"(sl + o0 + h * 1024), "r"(ob[0][h]), "r"(ob[1][h]), "r"(ob[2][h]), "r"(ob[3][h]) : "memory");
            asm volatile("st.shared.v4.u32 [%0], {%1,%2,%3,%4};" ::"r"(sl + o0 + h * 1024 + 512), "r"(ob[4][h]), "r"(ob[5][h]), "r"(ob[6][h]), "r"(ob[7][h]) : "memory");
            asm volatile("st.shared.v2.u32 [%0], {%1,%2};" ::"r"(sl + o1 + h * 256), "r"(ob[8][h]), "r"(ob[9][h]) : "memory");
        }
        fence_async_smem();
        __syncwarp();
        TSTAMP1T(4, 64);
        TSTAMP1(1);
        TSTAMP2(1);
        const unsigned char* ot = reinterpret_cast<const unsigned char*>(of) + mb * 163840 + wg * 10240;
        if (lane == 0) {
            asm volatile("cp.async.bulk.global.shared::cta.bulk_group [%0], [%1], 2048;" ::"l"(ot + hg * 20480 + (warp & 3) * 2048), "r"(sl + (warp & 3) * 2048) : "memory");
            asm volatile("cp.async.bulk.global.shared::cta.bulk_group [%0], [%1], 512;" ::"l"(ot + hg * 20480 + 8192 + (warp & 3) * 512), "r"(sl + 8192 + (warp & 3) * 512) : "memory");
            asm volatile("cp.async.bulk.commit_group;" ::: "memory");
            if (wg == 0) mbar_arrive(bar_pv);
            asm volatile("cp.async.bulk.wait_group 0;" ::: "memory");
            asm volatile(A1_FRED " [%0], 1;" ::"l"(reinterpret_cast<uint32_t*>(rsum + 2 * SEQ) + (((layer * 16 + mb) * 2 + wg) * 8 + hg) * FSTR) : "memory");
            DBGC(4 + warp);
        }
        TSTAMP4(11);
        float ac2[40];
        const uint64_t db0 = make_desc(sbase, 1024, 256, 3), db1 = make_desc(sbase + 10240, 512, 256, 3), da0 = make_desc(sl, 16, 1024, 2), da1 = make_desc(sl + 8192, 16, 256, 3);
        const uint32_t o7 = wg ? 640 : (A1_SM_W0 - A1_SM_A0) >> 4;
        const uint32_t trow = ((lane & 7) + 8 * (lane >> 4)) * 128 + (((2 * (warp & 3) + ((lane >> 3) & 1)) ^ (lane & 7)) << 4);
        uint32_t xr[10][2];
        mbar_wait(bar_f2 + 64 * wg + 64, 0);
        if (layer == 0) {
#pragma unroll
            for (int j = 0; j < 10; j += 2) ldsm_x4(&xr[j][0], sl + 51200 + (16 * (warp & 3) + (lane & 15)) * 160 + (lane >> 4) * 16 + 16 * j);
        } else {
#pragma unroll
            for (int j = 0; j < 10; j += 2) ldsm_x4_t(&xr[j][0], sl + 51200 + trow + 1024 * j);
        }
        const uint32_t ri = __shfl_sync(~0u, layer * SEQ + (wg * 2 + ((g >> 1) & 1)) * 512 + (mb * 16 + 4 * (warp & 3) + (g >> 2)) * 2 + (g & 1), lane);
        mbar_wait(bar_wo, 0);
        if (wg) mbar_wait(bar_pv, 0);
        if (wg) asm volatile("bar.sync 2, 128;" ::: "memory"); else asm volatile("bar.sync 1, 128;" ::: "memory");
        TSTAMP2(2);
#pragma unroll
        for (int q = 0; q < 8; q++) {
            uint32_t bo = wo_off(0) >> 4;
            if (q) {
                mbar_wait(bar_f2 + 64 * wg + 8 * q, 0);
                asm volatile("ld.shared.u32 %0, [%1];" : "=r"(bo) : "r"(que + 32 * wg + 4 * q) : "memory");
                bo = __shfl_sync(~0u, bo, 0);
                TSTAMP4(q);
                if (q == 1 && (tid & 127) == 0) DBGC(29 + 8 * wg);
            }
            wgmma_fence();
#pragma unroll
            for (int j = 0; j < 5; j++) wgmma_n80(ac2, (j < 4 ? da0 : da1) + (q == 7 ? o7 : 0u) + (uint64_t)((q < 6 ? q * 640 : 0) + (j & 2) * 16 + (j & 1) * 2), (j < 4 ? db0 : db1) + bo + (uint64_t)((j & 2) * 160 + (j & 1) * 32), j || q);
            wgmma_commit();
            if (q == 0) {
                wgmma_wait<0>();
                if ((tid & 127) == 0) { mbar_arrive(bar_e2 + 16 * wg); mbar_arrive(bar_e2 + 8); }
            }
            if (q == 2 && wg) {
                wgmma_wait<1>();
                if (tid == 128) mbar_arrive(bar_e2 + 24);
            }
        }
        if ((tid & 127) == 0) DBGC(28 + wg * 8 + 7);
        TSTAMP2(3);
        wgmma_wait<0>();
        TSTAMP2(4);
        if (__any_sync(~0u, ac2[0] != ac2[0] || ac2[2] != ac2[2])) {
#pragma unroll
            for (int i = 0; i < 40; i++) ac2[i] = 0.f;
            uint32_t a[20], an[20];
            auto lda = [&](uint32_t (&r)[20], int h) {
#pragma unroll
                for (int u = 0; u < 4; u++)
                    asm volatile("ld.relaxed.gpu.global.v4.u32 {%0,%1,%2,%3}, [%4];" : "=r"(r[4 * u]), "=r"(r[4 * u + 1]), "=r"(r[4 * u + 2]), "=r"(r[4 * u + 3]) : "l"(ot + h * 20480 + o0 + u * 512) : "memory");
#pragma unroll
                for (int u = 0; u < 2; u++)
                    asm volatile("ld.relaxed.gpu.global.v2.u32 {%0,%1}, [%2];" : "=r"(r[16 + 2 * u]), "=r"(r[17 + 2 * u]) : "l"(ot + h * 20480 + o1 + u * 256) : "memory");
            };
            lda(an, 0);
#pragma unroll 5
            for (int k = lane; k < WOB / 16; k += 32)
                reinterpret_cast<uint4*>(stg + (sl - sbase))[k] = __ldcg(reinterpret_cast<const uint4*>(wo + hg * 8 * WOB) + k);
            __syncwarp();
#pragma unroll 1
            for (int h = 0; h < 8; h++) {
#pragma unroll 1
                for (int it = 0; it < SPIN_MAX; it++) {
                    uint32_t m = 0;
#pragma unroll
                    for (int k = 0; k < 20; k += 2) m = __vimax3_u32(m, an[k], an[k + 1]);
                    if (!__any_sync(~0u, m == ~0u)) break;
                    lda(an, h);
                }
#pragma unroll
                for (int k = 0; k < 20; k++) a[k] = an[k];
                lda(an, min(h + 1, 7));
                const uint32_t bp = h == hg ? sl : sbase + wo_off(h + (h < hg));
                const int r0 = 8 * ((lane & 7) >> 1) + 2 * (lane >> 3) + (lane & 1), r2 = 4 * ((lane & 7) >> 1) + 2 * ((lane >> 3) & 1) + (lane & 1);
#pragma unroll
                for (int n = 0; n < 10; n++) {
                    uint32_t b[12];
                    ldsm_x4_t(b, bp + (n >> 1) * 1024 + r0 * 32 + (((n ^ (r0 >> 2)) & 1) << 4));
                    ldsm_x4_t(b + 4, bp + 5120 + (n >> 1) * 1024 + r0 * 32 + (((n ^ (r0 >> 2)) & 1) << 4));
                    ldsm_x4_t(b + 8, bp + 10240 + (n >> 1) * 512 + r2 * 32 + (((n ^ (r2 >> 2)) & 1) << 4));
                    mma_bf16(ac2 + 4 * n, a[0], a[8], a[1], a[9], b[0], b[1]); mma_bf16(ac2 + 4 * n, a[2], a[10], a[3], a[11], b[2], b[3]);
                    mma_bf16(ac2 + 4 * n, a[4], a[12], a[5], a[13], b[4], b[5]); mma_bf16(ac2 + 4 * n, a[6], a[14], a[7], a[15], b[6], b[7]);
                    mma_bf16(ac2 + 4 * n, a[16], a[18], a[17], a[19], b[8], b[9]);
                }
            }
        }
#pragma unroll
        for (int j = 0; j < 10; j++)
#pragma unroll
            for (int hh = 0; hh < 2; hh++) {
                const uint32_t a = pack2(ac2[4 * j + 2 * hh], ac2[4 * j + 2 * hh + 1]);
                const __nv_bfloat162 r = __hadd2_rn(*reinterpret_cast<const __nv_bfloat162*>(&xr[j][hh]), *reinterpret_cast<const __nv_bfloat162*>(&a));
                xr[j][hh] = *reinterpret_cast<const uint32_t*>(&r);
            }
        const uint32_t so = sl + 30720;
#pragma unroll
        for (int j = 0; j < 10; j += 2) stsm_x4_t(so + trow + 1024 * j, xr[j][0], xr[j][1], xr[j + 1][0], xr[j + 1][1]);
        fence_async_smem();
        if (wg) asm volatile("bar.sync 2, 128;" ::: "memory"); else asm volatile("bar.sync 1, 128;" ::: "memory");
        TSTAMP2(5);
        if ((tid & 127) == 0) {
            asm volatile("cp.async.bulk.tensor.2d.global.shared::cta.bulk_group [%0, {%1, %2}], [%3];" ::"l"(&tmX1), "r"(mb * 128 + 64 * wg), "r"(hg * 80), "r"(so) : "memory");
            asm volatile("cp.async.bulk.commit_group;" ::: "memory");
        }
        __syncwarp();
        const float p0 = *(volatile const float*)&rw[g].x, p1 = *(volatile const float*)&rw[g + 8].x;
        float s[3][4] = {};
        const uint32_t pp[2] = {__byte_perm(__float_as_uint(p0), 0, 0x3232), __byte_perm(__float_as_uint(p1), 0, 0x3232)};
#pragma unroll
        for (int j = 0; j < 10; j += 2) {
            const uint32_t d0 = sub2(xr[j][0], pp[0]), d1 = sub2(xr[j][1], pp[1]), d2 = sub2(xr[j + 1][0], pp[0]), d3 = sub2(xr[j + 1][1], pp[1]);
            mma_bf16(s[0], xr[j][0], xr[j][1], xr[j + 1][0], xr[j + 1][1], 0x3f803f80u, 0x3f803f80u);
            mma_bf16(s[1], d0, d1, d2, d3, d0, d2);
            mma_bf16(s[2], d0, d1, d2, d3, d1, d3);
        }
        if (t == (g >> 1)) {
            float2* rp = rsum + ri;
            asm volatile("red.relaxed.gpu.global.add.v2.f32 [%0], {%1, %2};" ::"l"(rp), "f"(fmaf(-80.f, p0, s[0][0])), "f"((g & 1) ? s[1][1] : s[1][0]) : "memory");
            asm volatile("red.relaxed.gpu.global.add.v2.f32 [%0], {%1, %2};" ::"l"(rp + 4), "f"(fmaf(-80.f, p1, s[0][2])), "f"((g & 1) ? s[2][3] : s[2][2]) : "memory");
        }
        asm volatile("cp.async.bulk.wait_group.read 0;" ::: "memory");
        TSTAMP2(6);
        if (tid == 0) DBGC(63);
        if (tid == 128) DBGC(28);
        if (tid == 0) DBGCAL(2);
        GSTAMP(g_tim1, 14);
        SPAN(1 + 4 * layer, 3);
    }
}

static int h_nsm;
static void* h_sym[11];
static TileTab h_tab;
static CUtensorMap h_tmX0, h_tmX1, h_tmR0, h_tmR1, h_tmX1st, h_tmOut, h_tmWq, h_tmWo, h_tmWt;
typedef CUresult (*PFN_encodeTiled)(CUtensorMap*, CUtensorMapDataType, cuuint32_t, void*, const cuuint64_t*, const cuuint64_t*,
                                    const cuuint32_t*, const cuuint32_t*, CUtensorMapInterleave, CUtensorMapSwizzle,
                                    CUtensorMapL2promotion, CUtensorMapFloatOOBfill);
static void make_tmap(CUtensorMap* tm, const void* ptr, uint64_t cols, uint64_t rows, uint32_t bc, uint32_t br, CUtensorMapSwizzle sw, uint64_t pitch = 0, uint64_t hi = 0, uint32_t bh = 2) {
    static PFN_encodeTiled fn = nullptr;
    if (!fn) {
        void* p = nullptr; cudaDriverEntryPointQueryResult qr;
        cudaGetDriverEntryPoint("cuTensorMapEncodeTiled", &p, cudaEnableDefault, &qr);
        fn = (PFN_encodeTiled)p;
    }
    if (br == 0) {
        cuuint64_t dims[5] = {16, 2, rows / 8, 4, cols / 16}; cuuint64_t strides[4] = {cols * 2, cols * 16, cols * 4, 32};
        cuuint32_t box[5] = {16, 2, bc, 4, 5}; cuuint32_t es[5] = {1, 1, 1, 1, 1};
        fn(tm, CU_TENSOR_MAP_DATA_TYPE_BFLOAT16, 5, const_cast<void*>(ptr), dims, strides, box, es, CU_TENSOR_MAP_INTERLEAVE_NONE, sw,
           CU_TENSOR_MAP_L2_PROMOTION_L2_128B, CU_TENSOR_MAP_FLOAT_OOB_FILL_NONE);
        return;
    }
    if (bh == 0) {
        cuuint64_t dims[5] = {64, 64, 2, 16, 10}; cuuint64_t strides[4] = {pitch * 2, hi * 2, cols * 2, rows * 2};
        cuuint32_t box[5] = {64, 64, 2, 1, 1}; cuuint32_t es[5] = {1, 1, 1, 1, 1};
        fn(tm, CU_TENSOR_MAP_DATA_TYPE_BFLOAT16, 5, const_cast<void*>(ptr), dims, strides, box, es, CU_TENSOR_MAP_INTERLEAVE_NONE, sw,
           CU_TENSOR_MAP_L2_PROMOTION_L2_128B, CU_TENSOR_MAP_FLOAT_OOB_FILL_NONE);
        return;
    }
    if (hi) {
        cuuint64_t dims[3] = {cols, rows, hi == 64 ? 32u : hi == 16 ? 120u : 2u}; cuuint64_t strides[2] = {pitch * 2, hi * 2};
        cuuint32_t box[3] = {bc, br, bh}; cuuint32_t es[3] = {1, 1, 1};
        fn(tm, CU_TENSOR_MAP_DATA_TYPE_BFLOAT16, 3, const_cast<void*>(ptr), dims, strides, box, es, CU_TENSOR_MAP_INTERLEAVE_NONE, sw,
           CU_TENSOR_MAP_L2_PROMOTION_L2_128B, CU_TENSOR_MAP_FLOAT_OOB_FILL_NONE);
        return;
    }
    cuuint64_t dims[2] = {cols, rows}; cuuint64_t strides[1] = {(pitch ? pitch : cols) * 2};
    cuuint32_t box[2] = {bc, br}; cuuint32_t es[2] = {1, 1};
    fn(tm, CU_TENSOR_MAP_DATA_TYPE_BFLOAT16, 2, const_cast<void*>(ptr), dims, strides, box, es, CU_TENSOR_MAP_INTERLEAVE_NONE, sw,
       CU_TENSOR_MAP_L2_PROMOTION_L2_128B, CU_TENSOR_MAP_FLOAT_OOB_FILL_NONE);
}
template <typename... Args>
static void launch_pdl(void (*kern)(Args...), int grid, int block, int smem, Args... args) {
    cudaLaunchConfig_t cfg = {};
    cfg.gridDim = dim3(grid); cfg.blockDim = dim3(block); cfg.dynamicSmemBytes = smem; cfg.stream = cudaStreamPerThread;
    cudaLaunchAttribute at[1];
    at[0].id = cudaLaunchAttributeProgrammaticStreamSerialization; at[0].val.programmaticStreamSerializationAllowed = 1;
    cfg.attrs = at; cfg.numAttrs = 1;
    cudaLaunchKernelEx(&cfg, kern, args...);
}
static void launch_stage(int k, void* const* d_in, void* d_out) {
    const KgIn kg = {(const bf16*)d_in[4], (const bf16*)d_in[5], (const bf16*)d_in[6], (const bf16*)d_in[7], (const bf16*)d_in[8], (const bf16*)d_in[9], (const bf16*)d_in[0], (const bf16*)d_in[1], (const bf16*)d_in[2],
                      (uint4*)h_sym[0], (uint4*)h_sym[1], (uint4*)h_sym[2], (uint4*)h_sym[3], (uint4*)h_sym[4], (float*)h_sym[5]};
    switch (k) {
        case 0: kgen_kernel<<<128, 512, KG_SMEM, cudaStreamPerThread>>>(kg, h_tmWq, h_tmWo, h_tmWt); break;
        case 1: launch_pdl(a1_kernel, h_nsm, A1_THREADS, A1_SMEM, 0, (const bf16*)d_in[0], (const unsigned char*)h_sym[1], (const unsigned char*)h_sym[2], (float2*)h_sym[4], (uint4*)h_sym[6], h_tmX0, h_tmR0, h_tmX1st, h_tab); break;
        case 3: launch_pdl(conv_kernel, DM / CV_CPB, CV_THREADS, CV_SMEM, 0, (const uint4*)h_sym[7], (const float4*)h_sym[4], (const bf16*)h_sym[8], (bf16*)h_sym[9], (const uint4*)h_sym[0], (bf16*)h_sym[10], h_tmOut); break;
        case 5: launch_pdl(a1_kernel, h_nsm, A1_THREADS, A1_SMEM, 1, (const bf16*)d_in[0], (const unsigned char*)h_sym[1], (const unsigned char*)h_sym[2], (float2*)h_sym[4], (uint4*)h_sym[6], h_tmX1, h_tmR1, h_tmX1st, h_tab); break;
        case 7: launch_pdl(conv_kernel, DM / CV_CPB, CV_THREADS, CV_SMEM, 1, (const uint4*)h_sym[7] + SEQ / 8, (const float4*)h_sym[4] + SEQ / 2, (const bf16*)h_sym[8], (bf16*)h_sym[10], (const uint4*)h_sym[0], (bf16*)h_sym[10], h_tmOut); break;
        default: break;
    }
}
static int n_stage_kernels() { return 9; }
static const char* stage_name(int k) { const char* n[] = {"kgen", "a1", "a2", "conv", "tr", "a1", "a2", "conv", "tr"}; return n[k]; }

extern "C" void kernel_launch(void* const* d_in, const int* in_sizes, int n_in, void* d_out, int out_size) {
    (void)in_sizes; (void)n_in; (void)out_size;
    static const void *p_in = nullptr, *p_w1 = nullptr, *p_w2 = nullptr, *p_out = nullptr;
    if (p_in != d_in[0] || p_w1 != d_in[1] || p_w2 != d_in[2] || p_out != d_out) {
        cudaFuncSetAttribute(conv_kernel, cudaFuncAttributeMaxDynamicSharedMemorySize, CV_SMEM);
        cudaFuncSetAttribute(kgen_kernel, cudaFuncAttributeMaxDynamicSharedMemorySize, KG_SMEM);
        cudaFuncSetAttribute(a1_kernel, cudaFuncAttributeMaxDynamicSharedMemorySize, A1_SMEM);
        int dev; cudaGetDevice(&dev); cudaDeviceGetAttribute(&h_nsm, cudaDevAttrMultiProcessorCount, dev);
        if (h_nsm != 132) h_nsm = 128;
        h_tab.ns = h_nsm == 132 ? 132 : ~0u;
        for (int i = 0; i < 264; i++) {
            const int h = (i - 64) >> 1;
            const int t = i >= 132 ? i - 132 : i < 64 ? ((i >> 1) & 7) * 16 + (i >> 4) * 2 + (i & 1) : i < 120 ? (1 + h % 7) * 16 + 8 + (h / 7) * 2 + (i & 1) : i < 124 ? 128 : i - 116;
            const int hg = (4 * (t >> 6) + (t & 3)) & 7;
            h_tab.e[i] = {(unsigned char)((t >> 2) & 15), (unsigned char)hg, (unsigned char)(5 * (hg >> 2)), (unsigned char)t, (uint32_t)(hg * 10 * WQ_STAGE)};
        }
        cudaGetSymbolAddress(&h_sym[0], g_tap); cudaGetSymbolAddress(&h_sym[1], g_wq); cudaGetSymbolAddress(&h_sym[2], g_wo);
        cudaGetSymbolAddress(&h_sym[3], g_halo); cudaGetSymbolAddress(&h_sym[4], g_sum); cudaGetSymbolAddress(&h_sym[5], g_csp); cudaGetSymbolAddress(&h_sym[6], g_of);
        cudaGetSymbolAddress(&h_sym[7], g_piv); cudaGetSymbolAddress(&h_sym[8], g_x1T); cudaGetSymbolAddress(&h_sym[9], g_xcT); cudaGetSymbolAddress(&h_sym[10], g_yT);
        void *px1, *px2;
        cudaGetSymbolAddress(&px1, g_x1T); cudaGetSymbolAddress(&px2, g_xcT);
        make_tmap(&h_tmX0, d_in[0], 128 * 640, 64, 64, 64, CU_TENSOR_MAP_SWIZZLE_128B, 1280, 640, 0);
        make_tmap(&h_tmX1, px2, 128, 64 * XCP, 64, 64, CU_TENSOR_MAP_SWIZZLE_128B, XCP, 64, 0);
        make_tmap(&h_tmR0, d_in[0], 640, 1024, 80, 64, CU_TENSOR_MAP_SWIZZLE_NONE, 1280, 640, 1);
        make_tmap(&h_tmR1, px2, 64, 640, 64, 80, CU_TENSOR_MAP_SWIZZLE_128B, XCP, 64, 1);
        make_tmap(&h_tmX1st, px1, 2048, 640, 64, 80, CU_TENSOR_MAP_SWIZZLE_128B, XCP);
        make_tmap(&h_tmWq, d_in[1], 16, 640, 16, 32, CU_TENSOR_MAP_SWIZZLE_32B, 1920, 16, 5);
        make_tmap(&h_tmWo, d_in[2], 640, 640, 4, 0, CU_TENSOR_MAP_SWIZZLE_32B);
        make_tmap(&h_tmWt, d_in[2], 640, 640, 2, 0, CU_TENSOR_MAP_SWIZZLE_32B);
        make_tmap(&h_tmOut, d_out, 640, 2048, 80, 8, CU_TENSOR_MAP_SWIZZLE_NONE);
        p_in = d_in[0]; p_w1 = d_in[1]; p_w2 = d_in[2]; p_out = d_out;
    }
    for (int k = 0; k < n_stage_kernels(); k++) launch_stage(k, d_in, d_out);
}
```

```cpp
#include <cuda_runtime.h>
#include <cuda_bf16.h>
#include <stdint.h>
#include <cuda.h>

typedef __nv_bfloat16 bf16;

constexpr int SEQ = 2048;
constexpr int DM = 640;
constexpr int NMODE = 192;

__device__ __forceinline__ float bf2f(bf16 v) { return __bfloat162float(v); }
__device__ __forceinline__ float rbf(float v) {
    uint32_t r;
    asm("cvt.rn.bf16x2.f32 %0, %1, %2;" : "=r"(r) : "f"(v), "f"(0.f));
    return __uint_as_float(r);
}
__device__ __forceinline__ uint32_t pack2(float lo, float hi) {
    __nv_bfloat162 t = __floats2bfloat162_rn(lo, hi);
    return *reinterpret_cast<uint32_t*>(&t);
}
__device__ __forceinline__ void pdl_sync() {
    asm volatile("griddepcontrol.wait;" ::: "memory");
    asm volatile("griddepcontrol.launch_dependents;" ::: "memory");
}
__device__ __forceinline__ float sqrt_apx(float v) { float r; asm("sqrt.approx.ftz.f32 %0, %1;" : "=f"(r) : "f"(v)); return r; }
__device__ __forceinline__ float rcp_apx(float v) { float r; asm("rcp.approx.ftz.f32 %0, %1;" : "=f"(r) : "f"(v)); return r; }
__device__ __forceinline__ uint32_t smem_u32(const void* p) { return (uint32_t)__cvta_generic_to_shared(p); }

constexpr int TAPB = 2 * 160 * 8;
__device__ __align__(128) uint4 g_tap[DM * 128];
#define XPAD 64
constexpr int XCP = SEQ + XPAD;
__device__ __align__(128) bf16 g_x1T[DM * XCP];
__device__ __align__(128) bf16 g_xcT[DM * XCP];
__device__ __align__(128) uint4 g_of[128 * 1280];
constexpr int WQ_STAGE = 240 * 128, WOB = 80 * 160;
__device__ __align__(128) uint4 g_wq[8 * 10 * WQ_STAGE / 16];
__device__ __align__(128) uint4 g_wo[64 * WOB / 16];
__device__ __align__(16) float g_csp[10 * 1920];
#define FSTR 32
__device__ __align__(128) float2 g_sum[2 * SEQ + 256 * FSTR];
__device__ __align__(16) bf16 g_piv[2 * SEQ];
__device__ __align__(128) bf16 g_yT[DM * XCP];
__device__ uint32_t g_epoch;
__device__ __align__(16) unsigned long long g_rstat[SEQ];
__device__ __align__(128) uint4 g_halo[640 * 148];
__device__ __forceinline__ unsigned long long tagw(uint32_t payload, uint32_t tag) { return ((unsigned long long)tag << 32) | payload; }
__device__ __forceinline__ ulonglong2 ld_tag2(const ulonglong2* p) {
    ulonglong2 v;
    asm volatile("ld.relaxed.gpu.global.v2.u64 {%0, %1}, [%2];" : "=l"(v.x), "=l"(v.y) : "l"(p) : "memory");
    return v;
}
__device__ __forceinline__ bool tag_ok(ulonglong2 v, uint32_t tag) { return (uint32_t)(v.x >> 32) == tag && (uint32_t)(v.y >> 32) == tag; }
__device__ __forceinline__ uint32_t ld_epoch() { uint32_t v; asm volatile("ld.relaxed.gpu.global.u32 %0, [%1];" : "=r"(v) : "l"(&g_epoch) : "memory"); return v + 1; }
constexpr int SPIN_MAX = 1 << 20;
__device__ uint32_t g_started[4];
__device__ __forceinline__ void sm_started(int slot) { asm volatile("red.relaxed.gpu.global.add.u32 [%0], 1;" ::"l"(g_started + slot) : "memory"); }
__device__ __noinline__ void sm_idle(int slot) {
    if (threadIdx.x) return;
    sm_started(slot);
    const uint32_t want = ld_epoch() * gridDim.x;
    pdl_sync();
#pragma unroll 1
    for (int it = 0; it < SPIN_MAX; it++) {
        uint32_t v;
        asm volatile("ld.relaxed.gpu.global.u32 %0, [%1];" : "=r"(v) : "l"(g_started + slot) : "memory");
        if ((int)(v - want) >= 0) break;
        __nanosleep(100);
    }
}
struct TileTab { uint32_t ns, pad; struct { unsigned char mb, hg, kb0, tile; uint32_t woff; } __align__(8) e[264]; };
__device__ __forceinline__ bool elect() {
    uint32_t p;
    asm volatile("{\n.reg .pred p;\nelect.sync _|p, 0xffffffff;\nselp.b32 %0, 1, 0, p;\n}" : "=r"(p));
    return p;
}
#define DBG_SYMS
#define TSTAMP(i)
#define TSTAMP1(i)
#define TSTAMP1T(i, t)
#define TSTAMP1X(i, t)
#define SPAN(k, i)
#define GSTAMP(arr, i)
#define TSTAMP2(i)
#define TSTAMP3(i)
#define TSTAMP4(i)
#define TSTAMPK(i, t)
#define TSTAMPC(i)
#define DBGC(i)
#define DBGV(i, v)
#define DBGCAL(i)

__device__ __forceinline__ void mma_bf16(float* d, uint32_t a0, uint32_t a1, uint32_t a2, uint32_t a3, uint32_t b0, uint32_t b1) {
    asm volatile("mma.sync.aligned.m16n8k16.row.col.f32.bf16.bf16.f32 {%0,%1,%2,%3}, {%4,%5,%6,%7}, {%8,%9}, {%0,%1,%2,%3};"
                 : "+f"(d[0]), "+f"(d[1]), "+f"(d[2]), "+f"(d[3]) : "r"(a0), "r"(a1), "r"(a2), "r"(a3), "r"(b0), "r"(b1));
}
__device__ __forceinline__ void mma_bf16_k8(float* d, uint32_t a0, uint32_t a1, uint32_t b0) {
    asm volatile("mma.sync.aligned.m16n8k8.row.col.f32.bf16.bf16.f32 {%0,%1,%2,%3}, {%4,%5}, {%6}, {%0,%1,%2,%3};"
                 : "+f"(d[0]), "+f"(d[1]), "+f"(d[2]), "+f"(d[3]) : "r"(a0), "r"(a1), "r"(b0));
}
__device__ __forceinline__ void ldsm_x4(uint32_t* r, uint32_t addr) {
    asm volatile("ldmatrix.sync.aligned.m8n8.x4.shared.b16 {%0,%1,%2,%3}, [%4];"
                 : "=r"(r[0]), "=r"(r[1]), "=r"(r[2]), "=r"(r[3]) : "r"(addr));
}

__device__ __forceinline__ void ldsm_x4_t(uint32_t* r, uint32_t addr) {
    asm volatile("ldmatrix.sync.aligned.m8n8.x4.trans.shared.b16 {%0,%1,%2,%3}, [%4];"
                 : "=r"(r[0]), "=r"(r[1]), "=r"(r[2]), "=r"(r[3]) : "r"(addr));
}
__device__ __forceinline__ void mbar_init(uint32_t bar, int count) { asm volatile("mbarrier.init.shared::cta.b64 [%0], %1;" ::"r"(bar), "r"(count)); }
__device__ __forceinline__ void mbar_arrive(uint32_t bar) { asm volatile("mbarrier.arrive.shared::cta.b64 _, [%0];" ::"r"(bar) : "memory"); }
__device__ __forceinline__ void mbar_wait(uint32_t bar, uint32_t parity) {
    asm volatile("{\n.reg .pred p;\nWAIT_LOOP:\n"
                 "mbarrier.try_wait.parity.shared::cta.b64 p, [%0], %1;\n"
                 "@p bra.uni WAIT_DONE;\nbra.uni WAIT_LOOP;\nWAIT_DONE:\n}" ::"r"(bar), "r"(parity) : "memory");
}

__device__ __forceinline__ void mbar_expect_tx(uint32_t bar, uint32_t bytes) {
    asm volatile("mbarrier.arrive.expect_tx.shared::cta.b64 _, [%0], %1;" ::"r"(bar), "r"(bytes) : "memory");
}
__device__ __forceinline__ void tma_load_2d(uint32_t dst, const void* tmap, int c0, int c1, uint32_t bar) {
    asm volatile("cp.async.bulk.tensor.2d.shared::cluster.global.mbarrier::complete_tx::bytes [%0], [%1, {%3, %4}], [%2];"
                 ::"r"(dst), "l"(tmap), "r"(bar), "r"(c0), "r"(c1) : "memory");
}
__device__ __forceinline__ void tma_load_3d(uint32_t dst, const void* tmap, int c0, int c1, int c2, uint32_t bar) {
    asm volatile("cp.async.bulk.tensor.3d.shared::cluster.global.mbarrier::complete_tx::bytes [%0], [%1, {%3, %4, %5}], [%2];"
                 ::"r"(dst), "l"(tmap), "r"(bar), "r"(c0), "r"(c1), "r"(c2) : "memory");
}
__device__ __forceinline__ void fence_async_smem() { asm volatile("fence.proxy.async.shared::cta;" ::: "memory"); }
__device__ __forceinline__ void bulk_load(uint32_t dst, const void* src, uint32_t bytes, uint32_t bar) {
    asm volatile("cp.async.bulk.shared::cluster.global.mbarrier::complete_tx::bytes [%0], [%1], %2, [%3];"
                 ::"r"(dst), "l"(src), "r"(bytes), "r"(bar) : "memory");
}
__device__ __forceinline__ void tma_store_2d(const void* tmap, int c0, int c1, uint32_t src) {
    asm volatile("cp.async.bulk.tensor.2d.global.shared::cta.bulk_group [%0, {%1, %2}], [%3];" ::"l"(tmap), "r"(c0), "r"(c1), "r"(src) : "memory");
    asm volatile("cp.async.bulk.commit_group;" ::: "memory");
    asm volatile("cp.async.bulk.wait_group.read 0;" ::: "memory");
}
__device__ __forceinline__ void stsm_x4(uint32_t addr, uint32_t r0, uint32_t r1, uint32_t r2, uint32_t r3) {
    asm volatile("stmatrix.sync.aligned.m8n8.x4.shared.b16 [%0], {%1,%2,%3,%4};" ::"r"(addr), "r"(r0), "r"(r1), "r"(r2), "r"(r3) : "memory");
}
__device__ __forceinline__ void stsm_x4_t(uint32_t addr, uint32_t r0, uint32_t r1, uint32_t r2, uint32_t r3) {
    asm volatile("stmatrix.sync.aligned.m8n8.x4.trans.shared.b16 [%0], {%1,%2,%3,%4};" ::"r"(addr), "r"(r0), "r"(r1), "r"(r2), "r"(r3) : "memory");
}
__device__ __forceinline__ void prefetch_tmap(const void* tmap) { asm volatile("prefetch.tensormap [%0];" ::"l"(tmap) : "memory"); }

__device__ __forceinline__ float2 cexp_at(float wr2, float wi, float p) {
    float er;
    asm("ex2.approx.ftz.f32 %0, %1;" : "=f"(er) : "f"(wr2 * p));
    float th = wi * p;
    const float k = rintf(th * 0.15915494309189535f);
    th = fmaf(k, -6.2831854820251465f, th);
    th = fmaf(k, 1.7484555314695172e-7f, th);
    return make_float2(er * __cosf(th), er * __sinf(th));
}
__device__ __forceinline__ float2 cmul(float2 a, float2 b) {
    return make_float2(fmaf(a.x, b.x, -a.y * b.y), fmaf(a.x, b.y, a.y * b.x));
}
__device__ __forceinline__ float2 csqr(float2 a) { return make_float2(fmaf(a.x, a.x, -a.y * a.y), (a.x + a.x) * a.y); }
__device__ __forceinline__ uint32_t packh(float2 v) {
    uint32_t r;
    asm("cvt.rn.f16x2.f32 %0, %1, %2;" : "=r"(r) : "f"(v.y), "f"(v.x));
    return r;
}
__device__ __forceinline__ void mma_f16(float* d, uint32_t a0, uint32_t a1, uint32_t a2, uint32_t a3, uint32_t b0, uint32_t b1) {
    asm volatile("mma.sync.aligned.m16n8k16.row.col.f32.f16.f16.f32 {%0,%1,%2,%3}, {%4,%5,%6,%7}, {%8,%9}, {%0,%1,%2,%3};"
                 : "+f"(d[0]), "+f"(d[1]), "+f"(d[2]), "+f"(d[3]) : "r"(a0), "r"(a1), "r"(a2), "r"(a3), "r"(b0), "r"(b1));
}

struct KgIn { const bf16 *logA, *Aim, *Cre, *Cim, *logdt, *dsk, *x, *wqkv, *wo; uint4 *tap, *wq, *wop, *halo, *sum; float* csp; };
constexpr int KG_THREADS = NMODE / 2;

constexpr int KG_BUF = 15 * 12288, KG_BAR = KG_BUF + 6 * 5120, KG_SMEM = KG_BAR + 64;
__global__ void __launch_bounds__(512, 1) kgen_kernel(const KgIn in, const __grid_constant__ CUtensorMap tmWq, const __grid_constant__ CUtensorMap tmWo,
                                                        const __grid_constant__ CUtensorMap tmWt) {
    extern __shared__ __align__(1024) uint4 tabs[];
#define KG_ROT 0
    const int lane = threadIdx.x & 31, w16 = (__shfl_sync(~0u, threadIdx.x >> 5, 0) + KG_ROT) & 15, grp = w16 / 3, warp = w16 - 3 * grp;
    const int d = blockIdx.x * 5 + grp, tid = warp * 32 + lane;
    uint4* tab = tabs + grp * (3 * 768);
    SPAN(0, 0); SPAN(0, 1);
    TSTAMPK(0, 0);
    asm volatile("griddepcontrol.launch_dependents;" ::: "memory");
    if (w16 == 15) {
        const uint32_t b0 = smem_u32(tab), wbar = b0 + 6 * 5120;
        const int blk = blockIdx.x, nq = blk < 112 ? 4 : 2, nj = nq + (blk < 64 ? 1 : 2);
        auto fetch = [&](int i) {
            const uint32_t dst = b0 + i * 5120, bar = wbar + 8 * i;
            if (i < nq) {
                const int p = blk + 64 * (i & 2), kb = p / 24;
                mbar_expect_tx(bar, 5120);
                tma_load_3d(dst, &tmWq, 0, kb * 64 + (i & 1) * 32, (p - 24 * kb) * 5, bar);
            } else if (i < nj) {
                const int o = i == nq ? blk : 255 - blk;
                mbar_expect_tx(bar, o < 128 ? 5120 : 2560);
                asm volatile("cp.async.bulk.tensor.5d.shared::cluster.global.mbarrier::complete_tx::bytes [%0], [%1, {%3, %3, %4, %3, %5}], [%2];"
                             ::"r"(dst), "l"(o < 128 ? &tmWo : &tmWt), "r"(bar), "r"(0), "r"((o & 7) * 10 + (o >> 6) * 4), "r"(((o >> 3) & 7) * 5) : "memory");
            }
        };
        const bool one = elect();
        if (one) {
#pragma unroll
            for (int i = 0; i < 6; i++) mbar_init(wbar + 8 * i, 1);
            asm volatile("fence.mbarrier_init.release.cluster;" ::: "memory");
#pragma unroll
            for (int i = 0; i < 6; i++) fetch(i);
        }
        __syncwarp();
#pragma unroll
        for (int i = 1; i <= 5; i++) asm volatile("bar.arrive %0, 128;" ::"r"(i) : "memory");
        if (one) {
#pragma unroll 1
            for (int i = 0; i < nj; i++) {
                const int p = blk + 64 * (i & 2), kb = p / 24, hg = p & 7, sec = (p - 24 * kb) >> 3, o = i == nq ? blk : 255 - blk, cg = (o >> 3) & 7, hb = o & 7;
                const unsigned char* dst = i < nq ? reinterpret_cast<unsigned char*>(in.wq) + (hg * 10 + (hg < 4 ? kb : kb < 5 ? kb + 5 : kb - 5)) * WQ_STAGE + ((i & 1) * 3 + sec) * 5120
                                                  : reinterpret_cast<unsigned char*>(in.wop) + (cg * 8 + (hb == cg ? 0 : hb + (hb < cg))) * WOB + (o >> 6) * 5120;
                mbar_wait(wbar + 8 * i, 0);
                if (i == 0) TSTAMPK(2, (15 - KG_ROT) * 32);
                if (i == 3) TSTAMPK(5, (15 - KG_ROT) * 32);
                asm volatile("cp.async.bulk.global.shared::cta.bulk_group [%0], [%1], %2;" ::"l"(dst), "r"(b0 + i * 5120), "r"(i < nq || o < 128 ? 5120 : 2560) : "memory");
            }
            asm volatile("cp.async.bulk.commit_group;" ::: "memory");
            asm volatile("cp.async.bulk.wait_group.read 0;" ::: "memory");
        }
        TSTAMPK(11, (15 - KG_ROT) * 32);
        return;
    }
    const bf16 pdt = in.logdt[d], pdsk = in.dsk[d];
    const uint32_t pla = reinterpret_cast<const uint32_t*>(in.logA)[d * KG_THREADS + tid], pai = reinterpret_cast<const uint32_t*>(in.Aim)[d * KG_THREADS + tid];
    const uint32_t pcr = reinterpret_cast<const uint32_t*>(in.Cre)[d * KG_THREADS + tid], pci = reinterpret_cast<const uint32_t*>(in.Cim)[d * KG_THREADS + tid];
    const bf16* pfq = tid < 30 ? in.wqkv + (size_t)(d * 30 + tid) * 64 : tid < 40 ? in.wo + (size_t)(d * 10 + tid - 30) * 64 : in.x + (size_t)(d * 32 + tid - 40) * 64;
#define KG_PF 0
    if (tid < (KG_PF == 3 ? 0 : KG_PF ? 40 : 72)) asm volatile("prefetch.global.L2 [%0];" ::"l"(pfq));
    asm volatile("st.global.v4.u32 [%0], {%1,%1,%1,%1};" ::"l"(in.halo + d * 148 + tid), "r"(~0u));
    if (tid < 52) asm volatile("st.global.v4.u32 [%0], {%1,%1,%1,%1};" ::"l"(in.halo + d * 148 + 96 + tid), "r"(~0u));
    else if (w16 == 2) {
        if (lane < 16) in.sum[blockIdx.x * 16 + lane] = make_uint4(0, 0, 0, 0);
        else if (lane < 20) reinterpret_cast<uint32_t*>(in.sum + 2048)[(blockIdx.x * 4 + lane - 16) * FSTR] = 0;
    }
    const uint32_t tw = smem_u32(tab) + warp * 12288;
    const int g = lane >> 2, t = lane & 3;
    const uint32_t sta = tw + lane * 128 + ((2 * (lane & 3) + ((lane >> 2) & 1)) << 4);
    const uint32_t lda = tw + t * 128 + ((g ^ (2 * t)) << 4);
    const uint32_t stb = tw + lane * 8, ldb = tw + g * 512 + (g & 3) * 32 + t * 8;
    auto sts4 = [&](int e, int off, uint32_t a, uint32_t b, uint32_t c, uint32_t dd) {
        asm volatile("st.shared.v4.u32 [%0], {%1,%2,%3,%4};" ::"r"((sta ^ (e << 4)) + off), "r"(a), "r"(b), "r"(c), "r"(dd) : "memory");
    };
    auto lds4 = [&](int sp, int off, uint32_t* r) {
        asm volatile("ld.shared.v4.u32 {%0,%1,%2,%3}, [%4];" : "=r"(r[0]), "=r"(r[1]), "=r"(r[2]), "=r"(r[3]) : "r"((lda ^ ((sp & 1) << 4)) + sp * 512 + off) : "memory");
    };
    const float dt = rbf(expf(bf2f(pdt)));
    float2 C[2], y1[2], z8[2], y128[2];
    float cmax = 0.f;
#pragma unroll
    for (int m = 0; m < 2; m++) {
        const float wr2 = -rbf(expf(__uint_as_float(m ? pla & 0xffff0000u : pla << 16))) * dt * 1.4426950408889634f;
        const float wi = __uint_as_float(m ? pai & 0xffff0000u : pai << 16) * dt;
        C[m] = make_float2(__uint_as_float(m ? pcr & 0xffff0000u : pcr << 16) * dt, -__uint_as_float(m ? pci & 0xffff0000u : pci << 16) * dt);
        cmax = fmaxf(cmax, fmaxf(fabsf(C[m].x), fabsf(C[m].y)));
        y1[m] = cexp_at(wr2, -wi, 1.f); z8[m] = cexp_at(wr2, wi, 8.f); y128[m] = cexp_at(wr2, -wi, 128.f);
    }
    const int ex = min(max((int)(__reduce_max_sync(~0u, __float_as_uint(cmax)) >> 23), 20), 240);
    const float scale = __uint_as_float((uint32_t)(127 + 10 + 127 - ex) << 23), unscale = 2.0f * __uint_as_float((uint32_t)(ex - 10) << 23);
    TSTAMPK(4, 64);
    if (KG_PF >= 2 && tid >= 40 && tid < 72) asm volatile("prefetch.global.L2 [%0];" ::"l"(pfq));
    float k2048 = 0.f;
    float acc[5][4];
#pragma unroll
    for (int j = 0; j < 5; j++)
#pragma unroll
        for (int k = 0; k < 4; k++) acc[j][k] = 0.f;
    uint32_t af[8][4];
    {
        float2 h0[2], h1[2], g0[2], g1[2], g2[2], g2b[2], g3[2], g4[2], y2[2], y4[2];
#pragma unroll
        for (int m = 0; m < 2; m++) {
            h0[m] = make_float2(1.f, 0.f); h1[m] = csqr(csqr(csqr(z8[m])));
            g0[m] = make_float2(C[m].x * scale, C[m].y * scale);
            g1[m] = cmul(g0[m], y128[m]);
            const float2 y256 = csqr(y128[m]), y512 = csqr(y256);
            g2b[m] = g2[m] = cmul(g0[m], y256); g3[m] = cmul(g0[m], y512); g4[m] = cmul(g3[m], y512);
            y2[m] = csqr(y1[m]); y4[m] = csqr(y2[m]);
            const float2 y1024 = csqr(y512);
            k2048 += fmaf(g4[m].x, y1024.x, -g4[m].y * y1024.y);
        }
#pragma unroll
        for (int e = 0; e < 8; e++) {
            sts4(e, 0, packh(h0[0]), packh(h1[0]), packh(h0[1]), packh(h1[1]));
            sts4(e, 4096, packh(g0[0]), packh(g0[1]), packh(g1[0]), packh(g1[1]));
#pragma unroll
            for (int m = 0; m < 2; m++)
                if (e < 7) { h0[m] = e ? cmul(h0[m], z8[m]) : z8[m]; h1[m] = cmul(h1[m], z8[m]); g0[m] = cmul(g0[m], y1[m]); g1[m] = cmul(g1[m], y1[m]); }
            if (e < 5) k2048 += __shfl_xor_sync(~0u, k2048, 1 << e);
        }
        if (KG_PF == 1 && tid >= 40 && tid < 72) asm volatile("prefetch.global.L2 [%0];" ::"l"(pfq));
        __syncwarp();
#pragma unroll
        for (int e = 0; e < 8; e++) {
            uint32_t b[4];
            lds4(e, 0, af[e]); lds4(e, 4096, b);
            sts4(e, 8192, packh(g2[0]), packh(g2[1]), packh((e & 1) ? cmul(g3[0], y4[0]) : g3[0]), packh((e & 1) ? cmul(g3[1], y4[1]) : g3[1]));
            asm volatile("st.shared.v2.u32 [%0], {%1,%2};" ::"r"((stb ^ ((e & 3) << 5)) + e * 512), "r"(packh(g4[0])), "r"(packh(g4[1])) : "memory");
#pragma unroll
            for (int m = 0; m < 2; m++)
                if (e < 7) {
                    g2[m] = e == 3 ? cmul(g2b[m], y128[m]) : cmul(g2[m], y2[m]);
                    if (e & 1) g3[m] = cmul(g3[m], y128[m]);
                    g4[m] = cmul(g4[m], y128[m]);
                }
            mma_f16(acc[0], af[e][0], af[e][1], af[e][2], af[e][3], b[0], b[1]);
            mma_f16(acc[1], af[e][0], af[e][1], af[e][2], af[e][3], b[2], b[3]);
        }
    }
    TSTAMPK(6, 64);
    __syncwarp();
#pragma unroll
    for (int sp = 0; sp < 8; sp++) {
        uint32_t c[4], e0, e1;
        lds4(sp, 8192, c);
        asm volatile("ld.shared.v2.u32 {%0,%1}, [%2];" : "=r"(e0), "=r"(e1) : "r"(ldb ^ (sp << 5)) : "memory");
        mma_f16(acc[2], af[sp][0], af[sp][1], af[sp][2], af[sp][3], c[0], c[1]);
        mma_f16(acc[3], af[sp][0], af[sp][1], af[sp][2], af[sp][3], c[2], c[3]);
        mma_f16(acc[4], af[sp][0], af[sp][1], af[sp][2], af[sp][3], e0, e1);
    }
    {
        float* Pp = reinterpret_cast<float*>(tab + warp * 768);
        auto sw = [](int i) { return i ^ ((i >> 2) & 24); };
#pragma unroll
        for (int h = 0; h < 2; h++) {
            const int b = g + 8 * h;
            *reinterpret_cast<float2*>(Pp + sw(8 * b + 2 * t)) = make_float2(acc[0][2 * h] * unscale, acc[0][2 * h + 1] * unscale);
            *reinterpret_cast<float2*>(Pp + 128 + sw(8 * b + 2 * t)) = make_float2(acc[1][2 * h] * unscale, acc[1][2 * h + 1] * unscale);
            *reinterpret_cast<float2*>(Pp + 256 + sw(4 * b + 2 * (t & 1) + 64 * (t >> 1))) = make_float2(acc[2][2 * h] * unscale, acc[2][2 * h + 1] * unscale);
            *reinterpret_cast<float2*>(Pp + 384 + sw(2 * b + 32 * t)) = make_float2(acc[3][2 * h] * unscale, acc[3][2 * h + 1] * unscale);
            Pp[512 + sw(b + 32 * t)] = acc[4][2 * h] * unscale;
            Pp[512 + sw(b + 32 * t + 16)] = acc[4][2 * h + 1] * unscale;
        }
        if (lane == 0) Pp[640] = k2048 * unscale;
    }
    TSTAMPK(7, 64);
    asm volatile("bar.sync %0, 128;" ::"r"(grp + 1) : "memory");
    TSTAMPK(9, 64);
    const float* Kp = reinterpret_cast<const float*>(tab);
    auto ksum = [&](int i) -> float { return (Kp[i] + Kp[3072 + i]) + Kp[6144 + i]; };
    auto ksum4 = [&](int q) -> float4 {
        q ^= (q >> 2) & 6;
        const float4 a = reinterpret_cast<const float4*>(Kp)[q], b = reinterpret_cast<const float4*>(Kp)[768 + q], c = reinterpret_cast<const float4*>(Kp)[1536 + q];
        return make_float4((a.x + b.x) + c.x, (a.y + b.y) + c.y, (a.z + b.z) + c.z, (a.w + b.w) + c.w);
    };
    {
        uint2* E4 = reinterpret_cast<uint2*>(in.tap + d * 128);
        float4 v = ksum4(tid), u = ksum4(96 + min(tid, 64));
        const float cor = rbf(ksum(tid == 95 ? 384 : 512));
        if (tid == 0) v.x += bf2f(pdsk);
        if (tid == 95) v.w -= cor;
        if (tid == 31) u.w -= cor;
        const uint32_t lo = pack2(v.x, v.y), hi = pack2(v.z, v.w);
        if (tid < 64) {
            E4[6 + tid] = make_uint2(lo, hi);
            E4[(tid < 32 ? 159 : 209 - 32) + tid] = make_uint2(pack2(u.x, u.y), pack2(u.z, u.w));
        } else {
            const uint32_t nx = __shfl_down_sync(~0u, lo, 1);
            in.tap[d * 128 + 35 + tid - 64] = make_uint4(__byte_perm(lo, 0, 0x1010), __byte_perm(lo, hi, 0x5432), __byte_perm(hi, 0, 0x1010), __byte_perm(hi, tid == 95 ? 0u : nx, 0x5432));
            if (tid == 64) E4[241] = make_uint2(pack2(u.x, 0.f), 0u);
        }
    }
    TSTAMPK(10, 64);
    if (warp < (blockIdx.x < 112 ? 2 : 1)) {
        const uint32_t sb = smem_u32(tabs);
        mbar_wait(sb + KG_BAR + 16 * warp, 0); mbar_wait(sb + KG_BAR + 16 * warp + 8, 0);
        uint32_t w[4][4];
        float cs[4] = {0.f, 0.f, 0.f, 0.f};
#pragma unroll
        for (int a = 0; a < 4; a++)
            ldsm_x4_t(w[a], sb + KG_BUF + warp * 10240 + grp * 1024 + ((lane >> 4) * 8 + (lane & 7)) * 32 + ((((lane >> 3) ^ (lane >> 2)) & 1) << 4) + (a >> 1) * 5120 + (a & 1) * 512);
#pragma unroll
        for (int a = 0; a < 4; a++) mma_bf16(cs, w[a][0], w[a][1], w[a][2], w[a][3], 0x3f803f80u, 0x3f803f80u);
        if (t < 2) in.csp[(blockIdx.x + 128 * warp) * 80 + grp * 16 + g + 8 * t] = t ? cs[2] : cs[0];
    }
    SPAN(0, 3);
}

#define CV_LD __ldcg
#define CV_LDX __ldcg
#define CV_SLEEP 100
#define CV_HAND 8
constexpr int CV_CPB = 5;
constexpr int CV_THREADS = 512;
constexpr int UPADF = 128;
constexpr int ULEN = UPADF + SEQ;
constexpr int XLEN = SEQ + 16;
constexpr int BX_5 = 0, BX_3 = 3264, BX_9 = 6528, BX_7 = 8960, BX_LEN = 11392;
constexpr int CV_SM_U = 0;
constexpr int CV_SM_T = CV_CPB * ULEN * 2;
constexpr int CV_SM_B = CV_SM_T + CV_CPB * TAPB;
constexpr int CV_SM_X = CV_SM_B + CV_CPB * BX_LEN;
constexpr int CV_SM_Y = (CV_SM_X + CV_CPB * XLEN * 2 + 127) & ~127;
constexpr int CV_SM_CNT = CV_SM_Y + CV_CPB * 8192;
constexpr int CV_SM_O = CV_SM_CNT + 128;
constexpr int CV_SMEM = CV_SM_O + 20480;
static_assert(ULEN % 128 == 0 && CV_SM_B % 128 == 0 && CV_SM_CNT % 128 == 0, "layout");

__device__ __forceinline__ uint32_t sub2(uint32_t x, uint32_t m) {
    const __nv_bfloat162 d = __hsub2(*reinterpret_cast<const __nv_bfloat162*>(&x), *reinterpret_cast<const __nv_bfloat162*>(&m));
    return *reinterpret_cast<const uint32_t*>(&d);
}
__device__ __forceinline__ uint32_t add2(uint32_t x, uint32_t y) {
    const __nv_bfloat162 d = __hadd2_rn(*reinterpret_cast<const __nv_bfloat162*>(&x), *reinterpret_cast<const __nv_bfloat162*>(&y));
    return *reinterpret_cast<const uint32_t*>(&d);
}
__device__ __forceinline__ void wgmma_fence() { asm volatile("wgmma.fence.sync.aligned;" ::: "memory"); }
__device__ __forceinline__ void wgmma_commit() { asm volatile("wgmma.commit_group.sync.aligned;" ::: "memory"); }
template <int N> __device__ __forceinline__ void wgmma_wait() { asm volatile("wgmma.wait_group.sync.aligned %0;" ::"n"(N) : "memory"); }
__device__ __forceinline__ uint64_t make_desc(uint32_t addr, uint32_t lbo, uint32_t sbo, uint32_t mode) {
    return (uint64_t)((addr & 0x3FFFF) >> 4) | ((uint64_t)(lbo >> 4) << 16) | ((uint64_t)(sbo >> 4) << 32) | ((uint64_t)mode << 62);
}
__device__ __forceinline__ void wgmma_rs128(float (&d)[64], uint2 hi, uint2 lo, uint64_t db, int acc) {
    asm volatile("{\n.reg .pred p;\nsetp.ne.b32 p, %69, 0;\nwgmma.mma_async.sync.aligned.m64n128k16.f32.bf16.bf16 {%0,%1,%2,%3,%4,%5,%6,%7,%8,%9,%10,%11,%12,%13,%14,%15,%16,%17,%18,%19,%20,%21,%22,%23,%24,%25,%26,%27,%28,%29,%30,%31,%32,%33,%34,%35,%36,%37,%38,%39,%40,%41,%42,%43,%44,%45,%46,%47,%48,%49,%50,%51,%52,%53,%54,%55,%56,%57,%58,%59,%60,%61,%62,%63}, {%64,%65,%66,%67}, %68, p, 1, 1, 0;\n}"
                 : "+f"(d[0]), "+f"(d[1]), "+f"(d[2]), "+f"(d[3]), "+f"(d[4]), "+f"(d[5]), "+f"(d[6]), "+f"(d[7]), "+f"(d[8]), "+f"(d[9]), "+f"(d[10]), "+f"(d[11]), "+f"(d[12]), "+f"(d[13]), "+f"(d[14]), "+f"(d[15]), "+f"(d[16]), "+f"(d[17]), "+f"(d[18]), "+f"(d[19]), "+f"(d[20]), "+f"(d[21]), "+f"(d[22]), "+f"(d[23]), "+f"(d[24]), "+f"(d[25]), "+f"(d[26]), "+f"(d[27]), "+f"(d[28]), "+f"(d[29]), "+f"(d[30]), "+f"(d[31]), "+f"(d[32]), "+f"(d[33]), "+f"(d[34]), "+f"(d[35]), "+f"(d[36]), "+f"(d[37]), "+f"(d[38]), "+f"(d[39]), "+f"(d[40]), "+f"(d[41]), "+f"(d[42]), "+f"(d[43]), "+f"(d[44]), "+f"(d[45]), "+f"(d[46]), "+f"(d[47]), "+f"(d[48]), "+f"(d[49]), "+f"(d[50]), "+f"(d[51]), "+f"(d[52]), "+f"(d[53]), "+f"(d[54]), "+f"(d[55]), "+f"(d[56]), "+f"(d[57]), "+f"(d[58]), "+f"(d[59]), "+f"(d[60]), "+f"(d[61]), "+f"(d[62]), "+f"(d[63])
                 : "r"(hi.x), "r"(hi.y), "r"(lo.x), "r"(lo.y), "l"(db), "r"(acc));
}
template <int V> struct Int { __device__ constexpr operator int() const { return V; } };
__device__ __forceinline__ void sts4(uint32_t a, const uint32_t* v) { asm volatile("st.shared.v4.u32 [%0], {%1,%2,%3,%4};" ::"r"(a), "r"(v[0]), "r"(v[1]), "r"(v[2]), "r"(v[3]) : "memory"); }
__device__ __forceinline__ int usw(int ch) { return ch ^ ((ch >> 3) & 1); }
__global__ void __launch_bounds__(CV_THREADS, 1) conv_kernel(int layer, const uint4* __restrict__ piv, const float4* __restrict__ sum, const bf16* __restrict__ x1T,
                                                             bf16* __restrict__ dst, const uint4* __restrict__ tap, bf16* __restrict__ yT, const __grid_constant__ CUtensorMap tmOut) {
    extern __shared__ __align__(1024) unsigned char sm[];
    SPAN(3 + 4 * layer, 0);
    bf16* Us = reinterpret_cast<bf16*>(sm + CV_SM_U);
    bf16* Xs = reinterpret_cast<bf16*>(sm + CV_SM_X);
#define CV_IDX int tid; asm volatile("mov.u32 %0, %tid.x;" : "=r"(tid)); \
    const int lane = tid & 31, warp = __shfl_sync(~0u, tid >> 5, 0), g = lane >> 2, ti = lane & 3; \
    const uint32_t* E4 = reinterpret_cast<const uint32_t*>(sm + CV_SM_O) + 307 + 2 * g - ti; (void)E4;
    const int d0 = blockIdx.x * CV_CPB, tile = blockIdx.x; (void)tile;
    const uint32_t cnt = smem_u32(sm + CV_SM_CNT);
    auto task_list = [](int w) {
        const uint32_t a = w < 8 ? (w < 4 ? 0x01021A18u : 0x08001B19u) : (w < 12 ? 0x0B030C04u : 0x14130A12u), b = w < 4 ? 0x101CFFFFu : w < 8 ? 0x0911FFFFu : ~0u;
        return __byte_perm(a, b, 0x4040 + 0x11 * (w & 3)) | 0xffff0000u;
    };
    TSTAMP1X(9, 256);
    if (threadIdx.x >= 256) {
        CV_IDX
        const int t2 = tid - 256, t7 = tid & 127, wgu = (warp >> 2) & 1;
        if (t2 == 0) {
            mbar_init(cnt + 48, 1);
            asm volatile("fence.mbarrier_init.release.cluster;" ::: "memory");
            mbar_expect_tx(cnt + 48, CV_CPB * 2048);
            bulk_load(smem_u32(sm + CV_SM_O), tap + d0 * 128, CV_CPB * 2048, cnt + 48);
        } else if (lane == 0) {
            if (warp < 15) mbar_init(cnt + 8 * (warp - 9), warp == 14 ? 8 : 4);
            else if (layer) prefetch_tmap(&tmOut);
        }
        if (t2 < 200) {
            const int k = t2;
            const int off = k < 20 ? CV_SM_B + BX_5 + 8 * k : k < 40 ? CV_SM_B + BX_3 + 8 * (k - 20) : k < 74 ? CV_SM_B + BX_9 + 8 * (k - 40) : k < 108 ? CV_SM_B + BX_7 + 8 * (k - 74)
                          : k < 140 ? CV_SM_U + 8 * (k - 108) : k < 156 ? CV_SM_T + 8 * (k - 140) : k < 186 ? CV_SM_T + 73 * 16 + 8 * (k - 156) : CV_SM_T + 153 * 16 + 8 * (k - 186);
            const int str = k < 108 ? BX_LEN : k < 140 ? ULEN * 2 : TAPB;
#pragma unroll
            for (int c = 0; c < CV_CPB; c++) *reinterpret_cast<uint2*>(sm + off + c * str) = make_uint2(0, 0);
        }
        fence_async_smem();
        asm volatile("bar.sync 1, 256;" ::: "memory");
        TSTAMP1X(10, 256);
        asm volatile("setmaxnreg.inc.sync.aligned.u32 168;");
        mbar_wait(cnt + 48, 0);
        TSTAMP1X(11, 256);
        {
            uint32_t w[3][4];
            const int cx = wgu ? min(t7 >> 1, 4) : 4, px = wgu ? t7 & 1 : t7 >> 6, rx = wgu ? 64 : t7 & 63;
#pragma unroll
            for (int k = 0; k < 3; k++) {
                const uint32_t* E2 = reinterpret_cast<const uint32_t*>(sm + CV_SM_O) + 11 + (k < 2 ? 512 * (wgu + 2 * k) + t7 + (t7 & 64) : 512 * cx + 128 * px + rx);
                w[k][0] = E2[0]; w[k][1] = E2[1]; w[k][2] = E2[64]; w[k][3] = E2[65];
                if (k < 2 ? (t7 & 63) == 0 : rx == 0) w[k][0] = w[k][2] = 0;
                if (k == 2 && wgu) w[k][1] = w[k][3] = 0;
            }
#pragma unroll
            for (int k = 0; k < 3; k++)
                *reinterpret_cast<uint4*>(sm + CV_SM_T + 128 + (k < 2 ? (wgu + 2 * k) * TAPB + t7 * 16 + (t7 & 64) * 4 : cx * TAPB + px * 1280 + rx * 16)) =
                    make_uint4(__byte_perm(w[k][1], w[k][0], 0x7610), __byte_perm(w[k][3], w[k][2], 0x7610), __byte_perm(w[k][1], 0, 0x1032), __byte_perm(w[k][3], 0, 0x1032));
        }
        asm volatile("bar.sync 1, 256;" ::: "memory");
        const uint2* Tc = reinterpret_cast<const uint2*>(sm + CV_SM_T + wgu * TAPB) + 16 + 80 * (warp & 2) + 8 * (warp & 1) + g - 2 * ti;
        uint2 fa[9][2], fn[9][2];
#pragma unroll
        for (int m = 0; m < 9; m++) { fa[m][0] = Tc[16 * m]; fa[m][1] = Tc[16 * m - 8]; }
#pragma unroll
        for (int m = 0; m < 9; m++) { fn[m][0] = Tc[TAPB / 4 + 16 * m]; fn[m][1] = Tc[TAPB / 4 + 16 * m - 8]; }
        TSTAMP1X(12, 256);
        uint32_t ya = smem_u32(sm + CV_SM_Y) + wgu * 8192 + (warp & 2) * 2048 + usw(2 * lane + (warp & 1)) * 16;
        uint64_t db = make_desc(smem_u32(Us + wgu * ULEN + UPADF), 16, 256, 3);
        if (wgu) asm volatile("bar.sync 3, 384;" ::: "memory");
        int c = wgu;
        auto chain = [&](const uint2 (&f)[9][2]) {
            float acc[64];
            asm volatile("bar.sync %0, %1;" ::"r"(c ? 4 + wgu : 2), "r"(c ? 256 : 384) : "memory");
            TSTAMPC(1 + 3 * c);
            wgmma_fence();
#pragma unroll
            for (int m = 0; m < 9; m++) {
                wgmma_rs128(acc, f[m][0], f[m][1], db - (uint64_t)(2 * m), m);
                if (m == CV_HAND && c < 4) asm volatile("bar.arrive %0, 256;" ::"r"(5 - wgu) : "memory");
            }
            wgmma_commit();
            asm volatile("griddepcontrol.launch_dependents;" ::: "memory");
            TSTAMPC(2 + 3 * c);
            wgmma_wait<0>();
            TSTAMPC(3 + 3 * c);
            uint32_t w[16];
#pragma unroll
            for (int j = 0; j < 16; j++) w[j] = j ? pack2(acc[4 * j] + acc[4 * j - 2], acc[4 * j + 1] + acc[4 * j - 1]) : pack2(acc[0], acc[1]);
#pragma unroll
            for (int j = 0; j < 16; j += 4) stsm_x4_t(ya + 256 * j, w[j], w[j + 1], w[j + 2], w[j + 3]);
            __syncwarp();
            if (lane == 0) mbar_arrive(cnt + 8 * c);
            c += 2; ya += 16384; db += ULEN / 4;
        };
#pragma unroll 1
        for (;;) {
            chain(fa);
            if (c > 4) break;
            if (c == 2) {
#pragma unroll
                for (int m = 0; m < 9; m++) { fa[m][0] = Tc[TAPB / 2 + 16 * m]; fa[m][1] = Tc[TAPB / 2 + 16 * m - 8]; }
            }
            chain(fn);
            if (c > 4) break;
        }
        TSTAMP1X(6, 256);
    } else {
        asm volatile("setmaxnreg.dec.sync.aligned.u32 88;");
        CV_IDX
        const uint4* ppv = piv + tid;
        const float4* psv = sum + tid;
        const uint2* pxv = reinterpret_cast<const uint2*>(x1T + (size_t)d0 * XCP) + (tid >> 4) * 32 + (tid & 15);
        asm volatile("st.shared.u64 [%0], %1;" ::"r"(smem_u32(Xs) + tid * 16), "l"((uint64_t)ppv ^ (uint64_t)psv ^ (uint64_t)pxv) : "memory");
        pdl_sync();
        SPAN(3 + 4 * layer, 1);
        TSTAMP(0);
        if (tid == 0) TSTAMPC(0);
        if (threadIdx.x == 0) { GSTAMP(g_tim, 15); }
        float4 sv[4];
#pragma unroll
        for (int k = 0; k < 4; k++) sv[k] = CV_LD(psv + 256 * k);
        const uint4 pv = CV_LD(ppv);
        uint2 xe[CV_CPB], xo[CV_CPB];
#pragma unroll
        for (int c = 0; c < CV_CPB; c++) { xe[c] = CV_LDX(pxv + c * (XCP / 4)); xo[c] = CV_LDX(pxv + c * (XCP / 4) + 16); }
        constexpr float idm = 1.0f / DM;
        uint32_t mw[4];
        float rs[8];
#pragma unroll
        for (int k = 0; k < 4; k++) {
            const uint32_t pw = k == 0 ? pv.x : k == 1 ? pv.y : k == 2 ? pv.z : pv.w;
            const float d0_ = sv[k].x * idm, d1_ = sv[k].z * idm;
            mw[k] = pack2(__uint_as_float(pw << 16) + d0_, __uint_as_float(pw & 0xffff0000u) + d1_);
            const uint32_t vr = pack2(fmaxf(fmaf(-d0_, d0_, sv[k].y * idm), 0.f), fmaxf(fmaf(-d1_, d1_, sv[k].w * idm), 0.f));
            const uint32_t ve = pack2(__uint_as_float(vr << 16) + 1e-5f, __uint_as_float(vr & 0xffff0000u) + 1e-5f);
            const uint32_t sd = pack2(sqrt_apx(__uint_as_float(ve << 16)), sqrt_apx(__uint_as_float(ve & 0xffff0000u)));
            rs[2 * k] = rcp_apx(__uint_as_float(sd << 16)); rs[2 * k + 1] = rcp_apx(__uint_as_float(sd & 0xffff0000u));
        }
        if (rs[0] != 123.f) TSTAMP(13);
        const uint32_t ua = smem_u32(Us) + usw(tid + UPADF / 8) * 16;
        uint32_t uw[CV_CPB][4];
#pragma unroll
        for (int c = 0; c < CV_CPB; c++) {
            const uint32_t e0 = sub2(xe[c].x, mw[0]), e1 = sub2(xe[c].y, mw[1]), o0 = sub2(xo[c].x, mw[2]), o1 = sub2(xo[c].y, mw[3]);
            uw[c][0] = pack2(__uint_as_float(e0 << 16) * rs[0], __uint_as_float(o0 << 16) * rs[4]); uw[c][1] = pack2(__uint_as_float(e0 & 0xffff0000u) * rs[1], __uint_as_float(o0 & 0xffff0000u) * rs[5]);
            uw[c][2] = pack2(__uint_as_float(e1 << 16) * rs[2], __uint_as_float(o1 << 16) * rs[6]); uw[c][3] = pack2(__uint_as_float(e1 & 0xffff0000u) * rs[3], __uint_as_float(o1 & 0xffff0000u) * rs[7]);
            asm volatile("st.shared.v4.u32 [%0], {%1,%2,%3,%4};" ::"r"(ua + c * ULEN * 2), "r"(uw[c][0]), "r"(uw[c][1]), "r"(uw[c][2]), "r"(uw[c][3]) : "memory");
            if (c == 0) {
                fence_async_smem();
                asm volatile("bar.arrive 2, 384;" ::: "memory");
                uint32_t zero;
                asm volatile("mov.u32 %0, %clock_hi;" : "=r"(zero));
#pragma unroll
                for (int k = 0; k < 4; k++) mw[k] += zero == ~0u;
            }
        }
        fence_async_smem();
        asm volatile("bar.sync 3, 384;" ::: "memory");
        TSTAMP(1);
#pragma unroll
        for (int c = 0; c < CV_CPB; c++) *reinterpret_cast<uint4*>(Xs + c * XLEN + tid * 8) = make_uint4(xe[c].x, xe[c].y, xo[c].x, xo[c].y);
        {
            const int chunk = warp < 6 ? tid : tid - 64;
            const uint32_t ea = smem_u32(Us) + usw(chunk + UPADF / 8 + (lane ? 1 : -1)) * 16, bx = smem_u32(sm + CV_SM_B) + chunk * 16;
            auto box = [&](auto c0, auto c1) {
                uint32_t lo[CV_CPB][4], hi[CV_CPB][2];
#pragma unroll
                for (int c = c0; c < c1; c++) {
                    lo[c][0] = 0;
#pragma unroll
                    for (int k = 1; k < 4; k++) lo[c][k] = __shfl_up_sync(~0u, uw[c][k], 1);
#pragma unroll
                    for (int k = 0; k < 2; k++) hi[c][k] = __shfl_down_sync(~0u, uw[c][k], 1);
                }
#pragma unroll
                for (int c = c0; c < c1; c++)
                    asm volatile("{\n.reg .pred p, q;\nsetp.eq.s32 p, %7, 0;\nsetp.eq.s32 q, %7, 31;\n@p ld.shared.v4.u32 {%0,%1,%2,%3}, [%6];\n@q ld.shared.v2.u32 {%4,%5}, [%6];\n}"
                                 : "+r"(lo[c][0]), "+r"(lo[c][1]), "+r"(lo[c][2]), "+r"(lo[c][3]), "+r"(hi[c][0]), "+r"(hi[c][1]) : "r"(ea + c * ULEN * 2), "r"(lane) : "memory");
#pragma unroll
                for (int c = c0; c < c1; c++) {
                    const uint32_t e[9] = {lo[c][1], lo[c][2], lo[c][3], uw[c][0], uw[c][1], uw[c][2], uw[c][3], hi[c][0], hi[c][1]};
                    uint32_t o[8], b[6];
#pragma unroll
                    for (int i = 0; i < 8; i++) o[i] = __byte_perm(e[i], e[i + 1], 0x5432);
#pragma unroll
                    for (int i = 0; i < 6; i++) b[i] = add2(add2(o[i], o[i + 1]), e[i + 1]);
                    sts4(bx + c * BX_LEN + BX_3 + 160, b);
#pragma unroll
                    for (int i = 2; i < 6; i++) b[i] = add2(b[i], add2(e[i], e[i + 2]));
                    sts4(bx + c * BX_LEN + BX_5 + 160, b + 2);
                    if (warp < 4) {
#pragma unroll
                        for (int i = 2; i < 6; i++) b[i] = add2(b[i], add2(o[i - 1], o[i + 2]));
                        sts4(bx + c * BX_LEN + BX_7 + 272, b + 2);
#pragma unroll
                        for (int i = 2; i < 6; i++) b[i] = add2(b[i], add2(e[i - 1], e[i + 3]));
                        sts4(bx + c * BX_LEN + BX_9 + 272, b + 2);
                    }
                }
            };
            if (warp < 6) box(Int<0>(), Int<3>());
            else {
#pragma unroll
                for (int c = 3; c < 5; c++) asm volatile("ld.shared.v4.u32 {%0,%1,%2,%3}, [%4];" : "=r"(uw[c][0]), "=r"(uw[c][1]), "=r"(uw[c][2]), "=r"(uw[c][3]) : "r"(ua - 1024 + c * ULEN * 2) : "memory");
                if (tid >= 256 - CV_CPB) {
                    const int c = 255 - tid;
                    const uint2 v = *reinterpret_cast<const uint2*>(Us + c * ULEN + UPADF);
                    const float s1 = __uint_as_float(v.x << 16), s2 = s1 + __uint_as_float(v.x & 0xffff0000u), s3 = s2 + __uint_as_float(v.y << 16), s4 = s3 + __uint_as_float(v.y & 0xffff0000u);
                    unsigned char* bc = sm + CV_SM_B + c * BX_LEN;
                    *reinterpret_cast<uint32_t*>(bc + BX_5 + 156) = pack2(s1, s2);
                    *reinterpret_cast<uint2*>(bc + BX_7 + 264) = make_uint2(v.x << 16, pack2(s2, s3));
                    *reinterpret_cast<uint2*>(bc + BX_9 + 264) = make_uint2(pack2(s1, s2), pack2(s3, s4));
                }
                __syncwarp();
            }
            if ((warp & 6) != 4) box(Int<3>(), Int<5>());
        }
        __syncwarp();
        if (lane == 0) mbar_arrive(cnt + 40);
        TSTAMP(2);
        if (layer == 0) {
#pragma unroll
            for (int c = 0; c < CV_CPB; c++) reinterpret_cast<uint4*>(yT + (size_t)(d0 + c) * XCP)[tid] = make_uint4(~0u, ~0u, ~0u, ~0u);
        } else if (blockIdx.x == 0 && tid == 192) g_epoch = ld_epoch();
        __syncwarp();
    }
    {
        CV_IDX
        uint32_t tasks = task_list(warp);
        uint32_t off2, off3, offc, offd;
        {
            const int mat = lane >> 3, r = lane & 7;
            const int j2 = 13 + (r ^ 1) + 8 * (mat >> 1), j3 = j2 + 2, i0 = 8 * (mat & 1);
            off2 = (j2 & 1) ? BX_3 + (4 * j2 + i0 + 84) * 2 : BX_5 + (4 * j2 + i0 + 80) * 2;
            off3 = ((j3 & 1) ? BX_7 : BX_9) + (8 * j3 + i0 + 136) * 2;
            offc = usw(16 * (mat >> 1) + 2 * r + (mat & 1)) * 16;
            offd = usw(16 * mat + 2 * r + 2) * 16;
        }
#pragma unroll 1
        for (; (tasks & 0xff) != 0xff; tasks >>= 8) {
            const int c = tasks & 7, Q = (tasks >> 3) & 3, b0 = 4 * Q;
            const uint32_t bbase = smem_u32(sm + CV_SM_B + c * BX_LEN);
            const uint32_t kk = reinterpret_cast<const uint32_t*>(sm + CV_SM_O)[512 * c + (Q ? 418 : 318)];
            unsigned char* yq = sm + CV_SM_Y + c * 8192 + Q * 1024;
            uint4 yv[2], xv[2];
            if (Q) {
                uint32_t f4[20], f8[18];
                {
                    const volatile uint32_t* e4 = E4 + 512 * c;
#pragma unroll
                    for (int k = 0; k < 20; k++) f4[k] = e4[4 * k];
                    if (Q > 1) {
#pragma unroll
                        for (int k = 0; k < 10; k++) f8[k] = e4[107 - g + 4 * k];
                    }
                    if (Q > 2) {
#pragma unroll
                        for (int k = 10; k < 18; k++) f8[k] = e4[107 - g + 4 * k];
                    }
                }
                mbar_wait(cnt + 40, 0);
                float acc[4][4];
#pragma unroll
                for (int j = 0; j < 4; j++)
#pragma unroll
                    for (int k = 0; k < 4; k++) acc[j][k] = 0.f;
                {
                    const uint32_t ab = bbase + off2 + (2 * b0 - 2) * 128;
                    uint32_t a[3][4];
                    ldsm_x4_t(a[0], ab);
                    ldsm_x4_t(a[1], ab - 128);
#pragma unroll
                    for (int kp = 0; kp < 16; kp++) {
                        if (kp == 9 && Q == 1) break;
                        if (kp < 7 || (kp < 14 && Q > 1)) ldsm_x4_t(a[(kp + 2) % 3], ab - (kp + 2) * 128);
#pragma unroll
                        for (int j = 0; j < 4; j++) {
                            const int ee = 2 * j - 6 + kp;
                            if (ee >= 0 && ee <= 9) mma_bf16(acc[j], a[kp % 3][0], a[kp % 3][1], a[kp % 3][2], a[kp % 3][3], f4[2 * ee + 1], f4[2 * ee]);
                        }
                    }
                }
                TSTAMP(7);
                if (Q > 1) {
                    const uint32_t ab = bbase + off3 + (b0 - 6) * 256;
                    uint32_t a[3][4];
                    ldsm_x4_t(a[0], ab);
                    ldsm_x4_t(a[1], ab - 256);
#pragma unroll
                    for (int kp = 0; kp < 9; kp++) {
                        if (kp == 5 && Q == 2) break;
                        if (kp < 3 || (kp < 7 && Q == 3)) ldsm_x4_t(a[(kp + 2) % 3], ab - (kp + 2) * 256);
#pragma unroll
                        for (int j = 0; j < 4; j++) {
                            const int dl = j - 3 + kp;
                            if (dl >= 0 && dl <= 8) mma_bf16(acc[j], a[kp % 3][0], a[kp % 3][1], a[kp % 3][2], a[kp % 3][3], f8[2 * dl + 1], f8[2 * dl]);
                        }
                    }
                    const int e = g - 2 * ti;
                    const uint32_t ub = smem_u32(Us + c * ULEN + UPADF) + (Q - 2) * 1024;
                    const uint32_t P = e == -5 ? kk & 0xffffu : e == -4 ? kk << 16 : 0u, S = e == 3 ? kk & 0xffffu : e == 4 ? kk << 16 : 0u;
                    uint32_t bq[12];
                    ldsm_x4(bq, ub + offc); ldsm_x4(bq + 4, ub + offc + 512); ldsm_x4(bq + 8, ub + offd);
#pragma unroll
                    for (int j = 0; j < 4; j++) {
                        mma_bf16(acc[j], P, 0u, S, P, bq[2 * j], bq[2 * j + 1]);
                        mma_bf16_k8(acc[j], 0u, S, bq[8 + j]);
                    }
                } else if (ti == 3)
                    acc[3][3] += __uint_as_float(kk << 16) * (bf2f(*reinterpret_cast<const bf16*>(sm + CV_SM_B + c * BX_LEN + BX_9 + (128 + g) * 2)) + bf2f(Us[c * ULEN + UPADF + (g < 3 ? -32 : g - 3)]));
                mbar_wait(cnt + 8 * c, 0);
                uint32_t yw[8], yz[8];
                ldsm_x4_t(yw, smem_u32(yq) + offc); ldsm_x4_t(yw + 4, smem_u32(yq) + offc + 512);
                ldsm_x4_t(yz, smem_u32(yq) + offc + 3584); ldsm_x4_t(yz + 4, smem_u32(yq) + offc + 4096);
                TSTAMP(8);
#pragma unroll
                for (int k = 0; k < 2; k++) xv[k] = *reinterpret_cast<const uint4*>(Xs + c * XLEN + 512 * Q + 256 * k + 8 * lane);
#pragma unroll
                for (int k = 0; k < 8; k++)  yw[k] = add2(add2(yw[k], yz[k]), pack2(acc[k >> 1][2 * (k & 1)], acc[k >> 1][2 * (k & 1) + 1]));
                stsm_x4_t(smem_u32(yq) + offc, yw[0], yw[1], yw[2], yw[3]);
                stsm_x4_t(smem_u32(yq) + offc + 512, yw[4], yw[5], yw[6], yw[7]);
                __syncwarp();
            } else {
                mbar_wait(cnt + 40, 0);
#pragma unroll
                for (int k = 0; k < 2; k++) xv[k] = *reinterpret_cast<const uint4*>(Xs + c * XLEN + 256 * k + 8 * lane);
                mbar_wait(cnt + 8 * c, 0);
            }
#pragma unroll
            for (int k = 0; k < 2; k++) yv[k] = *reinterpret_cast<const uint4*>(yq + 512 * k + usw(lane) * 16);
            if (Q == 0) {
                const uint4 yz = *reinterpret_cast<const uint4*>(yq + 4096 + usw(lane) * 16);
                const uint32_t b5 = *reinterpret_cast<const uint32_t*>(sm + CV_SM_B + c * BX_LEN + BX_5 + (lane == 31 ? 156 : 0));
                yv[1].x = add2(yv[1].x, yz.x); yv[1].y = add2(yv[1].y, yz.y); yv[1].z = add2(yv[1].z, yz.z);
                yv[1].w = pack2(fmaf(__uint_as_float(kk << 16), __uint_as_float(b5 << 16), __uint_as_float(yv[1].w << 16) + __uint_as_float(yz.w << 16)),
                                fmaf(__uint_as_float(kk << 16), __uint_as_float(b5 & 0xffff0000u), __uint_as_float(yv[1].w & 0xffff0000u) + __uint_as_float(yz.w & 0xffff0000u)));
            }
#pragma unroll
            for (int k = 0; k < 2; k++) {
                if (layer)
                    asm volatile("st.relaxed.gpu.global.v4.u32 [%0], {%1,%2,%3,%4};" ::"l"(dst + (size_t)(d0 + c) * XCP + 512 * Q + 256 * k + 8 * lane),
                                 "r"(add2(__byte_perm(xv[k].x, xv[k].z, 0x5410), yv[k].x)), "r"(add2(__byte_perm(xv[k].x, xv[k].z, 0x7632), yv[k].y)),
                                 "r"(add2(__byte_perm(xv[k].y, xv[k].w, 0x5410), yv[k].z)), "r"(add2(__byte_perm(xv[k].y, xv[k].w, 0x7632), yv[k].w)) : "memory");
                else {
                    uint2* dp = reinterpret_cast<uint2*>(dst + (size_t)(d0 + c) * XCP + 512 * Q + 256 * k) + (lane >> 4) * 32 + (lane & 15);
                    dp[0] = make_uint2(add2(xv[k].x, __byte_perm(yv[k].x, yv[k].y, 0x5410)), add2(xv[k].y, __byte_perm(yv[k].z, yv[k].w, 0x5410)));
                    dp[16] = make_uint2(add2(xv[k].z, __byte_perm(yv[k].x, yv[k].y, 0x7632)), add2(xv[k].w, __byte_perm(yv[k].z, yv[k].w, 0x7632)));
                }
            }
        }
        TSTAMP(4);
        if (layer == 1) {
            const int mb = blockIdx.x >> 3, cg = blockIdx.x & 7;
            const bf16* src = dst + (size_t)(cg * 80 + (tid >> 4)) * XCP + mb * 128 + (tid & 15) * 8;
            uint32_t v[3][4];
            __syncthreads();
            uint32_t todo = warp < 8 ? 7 : 3;
#pragma unroll 1
            for (int it = 0; it < SPIN_MAX; it++) {
#pragma unroll
                for (int k = 0; k < 3; k++)
                    if (todo >> k & 1)
                        asm volatile("ld.relaxed.gpu.global.v4.u32 {%0,%1,%2,%3}, [%4];" : "=r"(v[k][0]), "=r"(v[k][1]), "=r"(v[k][2]), "=r"(v[k][3]) : "l"(src + k * (32 * XCP)) : "memory");
#pragma unroll
                for (int k = 0; k < 3; k++)
                    if ((todo >> k & 1) && v[k][0] != ~0u && v[k][1] != ~0u && v[k][2] != ~0u && v[k][3] != ~0u) {
                        *reinterpret_cast<uint4*>(sm + (32 * k + (tid >> 4)) * 272 + (tid & 15) * 16) = make_uint4(v[k][0], v[k][1], v[k][2], v[k][3]);
                        todo ^= 1u << k;
                    }
                if (!todo) break;
                __nanosleep(CV_SLEEP);
            }
            __syncthreads();
            uint32_t w[12];
#pragma unroll
            for (int k = 0; k < 3; k++) ldsm_x4(&w[4 * k], smem_u32(sm) + min(32 * k + lane, 79) * 272 + warp * 16);
            const uint32_t ot = smem_u32(sm + CV_SM_O) + warp * 1280, oa = ot + (lane & 7) * 160 + (lane >> 3) * 16;
            stsm_x4_t(oa, w[0], w[1], w[2], w[3]);
            stsm_x4_t(oa + 64, w[4], w[5], w[6], w[7]);
            asm volatile("stmatrix.sync.aligned.m8n8.x2.trans.shared.b16 [%0], {%1,%2};" ::"r"(oa + 128), "r"(w[8]), "r"(w[9]) : "memory");
            fence_async_smem();
            __syncwarp();
            if (lane == 0) tma_store_2d(&tmOut, cg * 80, mb * 128 + 8 * warp, ot);
        }
    }
    TSTAMP(3);
    GSTAMP(g_tim, 14);
    SPAN(3 + 4 * layer, 3);
}

template <int TA, int TB>
__device__ __forceinline__ void wgmma_n240(float (&d)[120], uint64_t da, uint64_t db, int acc) {
    asm volatile("{\n.reg .pred p;\nsetp.ne.b32 p, %124, 0;\nwgmma.mma_async.sync.aligned.m64n240k16.f32.bf16.bf16 {%0,%1,%2,%3,%4,%5,%6,%7,%8,%9,%10,%11,%12,%13,%14,%15,%16,%17,%18,%19,%20,%21,%22,%23,%24,%25,%26,%27,%28,%29,%30,%31,%32,%33,%34,%35,%36,%37,%38,%39,%40,%41,%42,%43,%44,%45,%46,%47,%48,%49,%50,%51,%52,%53,%54,%55,%56,%57,%58,%59,%60,%61,%62,%63,%64,%65,%66,%67,%68,%69,%70,%71,%72,%73,%74,%75,%76,%77,%78,%79,%80,%81,%82,%83,%84,%85,%86,%87,%88,%89,%90,%91,%92,%93,%94,%95,%96,%97,%98,%99,%100,%101,%102,%103,%104,%105,%106,%107,%108,%109,%110,%111,%112,%113,%114,%115,%116,%117,%118,%119}, %120, %121, p, 1, 1, %122, %123;\n}"
                 : "+f"(d[0]), "+f"(d[1]), "+f"(d[2]), "+f"(d[3]), "+f"(d[4]), "+f"(d[5]), "+f"(d[6]), "+f"(d[7]), "+f"(d[8]), "+f"(d[9]), "+f"(d[10]), "+f"(d[11]), "+f"(d[12]), "+f"(d[13]), "+f"(d[14]), "+f"(d[15]), "+f"(d[16]), "+f"(d[17]), "+f"(d[18]), "+f"(d[19]), "+f"(d[20]), "+f"(d[21]), "+f"(d[22]), "+f"(d[23]), "+f"(d[24]), "+f"(d[25]), "+f"(d[26]), "+f"(d[27]), "+f"(d[28]), "+f"(d[29]), "+f"(d[30]), "+f"(d[31]), "+f"(d[32]), "+f"(d[33]), "+f"(d[34]), "+f"(d[35]), "+f"(d[36]), "+f"(d[37]), "+f"(d[38]), "+f"(d[39]), "+f"(d[40]), "+f"(d[41]), "+f"(d[42]), "+f"(d[43]), "+f"(d[44]), "+f"(d[45]), "+f"(d[46]), "+f"(d[47]), "+f"(d[48]), "+f"(d[49]), "+f"(d[50]), "+f"(d[51]), "+f"(d[52]), "+f"(d[53]), "+f"(d[54]), "+f"(d[55]), "+f"(d[56]), "+f"(d[57]), "+f"(d[58]), "+f"(d[59]), "+f"(d[60]), "+f"(d[61]), "+f"(d[62]), "+f"(d[63]), "+f"(d[64]), "+f"(d[65]), "+f"(d[66]), "+f"(d[67]), "+f"(d[68]), "+f"(d[69]), "+f"(d[70]), "+f"(d[71]), "+f"(d[72]), "+f"(d[73]), "+f"(d[74]), "+f"(d[75]), "+f"(d[76]), "+f"(d[77]), "+f"(d[78]), "+f"(d[79]), "+f"(d[80]), "+f"(d[81]), "+f"(d[82]), "+f"(d[83]), "+f"(d[84]), "+f"(d[85]), "+f"(d[86]), "+f"(d[87]), "+f"(d[88]), "+f"(d[89]), "+f"(d[90]), "+f"(d[91]), "+f"(d[92]), "+f"(d[93]), "+f"(d[94]), "+f"(d[95]), "+f"(d[96]), "+f"(d[97]), "+f"(d[98]), "+f"(d[99]), "+f"(d[100]), "+f"(d[101]), "+f"(d[102]), "+f"(d[103]), "+f"(d[104]), "+f"(d[105]), "+f"(d[106]), "+f"(d[107]), "+f"(d[108]), "+f"(d[109]), "+f"(d[110]), "+f"(d[111]), "+f"(d[112]), "+f"(d[113]), "+f"(d[114]), "+f"(d[115]), "+f"(d[116]), "+f"(d[117]), "+f"(d[118]), "+f"(d[119])
                 : "l"(da), "l"(db), "n"(TA), "n"(TB), "r"(acc));
}

__device__ __forceinline__ void wgmma_n80(float (&d)[40], uint64_t da, uint64_t db, int acc) {
    asm volatile("{\n.reg .pred p;\nsetp.ne.b32 p, %42, 0;\nwgmma.mma_async.sync.aligned.m64n80k16.f32.bf16.bf16 {%0,%1,%2,%3,%4,%5,%6,%7,%8,%9,%10,%11,%12,%13,%14,%15,%16,%17,%18,%19,%20,%21,%22,%23,%24,%25,%26,%27,%28,%29,%30,%31,%32,%33,%34,%35,%36,%37,%38,%39}, %40, %41, p, 1, 1, 0, 1;\n}"
                 : "+f"(d[0]), "+f"(d[1]), "+f"(d[2]), "+f"(d[3]), "+f"(d[4]), "+f"(d[5]), "+f"(d[6]), "+f"(d[7]), "+f"(d[8]), "+f"(d[9]), "+f"(d[10]), "+f"(d[11]), "+f"(d[12]), "+f"(d[13]), "+f"(d[14]), "+f"(d[15]), "+f"(d[16]), "+f"(d[17]), "+f"(d[18]), "+f"(d[19]), "+f"(d[20]), "+f"(d[21]), "+f"(d[22]), "+f"(d[23]), "+f"(d[24]), "+f"(d[25]), "+f"(d[26]), "+f"(d[27]), "+f"(d[28]), "+f"(d[29]), "+f"(d[30]), "+f"(d[31]), "+f"(d[32]), "+f"(d[33]), "+f"(d[34]), "+f"(d[35]), "+f"(d[36]), "+f"(d[37]), "+f"(d[38]), "+f"(d[39])
                 : "l"(da), "l"(db), "r"(acc));
}

constexpr int A1_THREADS = 384;
constexpr int A1_NST = 4;
#define A1_SKEW 8
constexpr int A1_STAGE = 16384 + WQ_STAGE;
constexpr int A1_KVP = 336;
constexpr int A1_SM_KV = 2 * A1_STAGE;
constexpr int A1_SM_BAR = A1_NST * A1_STAGE;
constexpr int A1_SM_RS = A1_SM_BAR + 512;
constexpr int A1_SM_W0 = A1_SM_BAR + 3072, A1_SM_W3 = A1_SM_BAR - 3 * WOB, A1_SM_A1 = 2 * WOB, A1_SM_A0 = A1_SM_A1 + 61440;
constexpr int A1_SM_XA = A1_SM_W0 + 2 * WOB, A1_SM_XB = A1_SM_XA + 2048;
constexpr int A1_SMEM = A1_SM_W0 + 3 * WOB;
static_assert(A1_SM_W3 >= A1_SM_KV + 144 * A1_KVP && A1_SM_W3 % 512 == 0 && A1_SM_A1 % 1024 == 0 && A1_SM_A0 <= A1_SM_KV && A1_SM_A0 + 61440 <= A1_SM_W3 && A1_SMEM <= 232448, "layout");
__device__ __forceinline__ constexpr uint32_t wo_off(int h) { return h * WOB + (h < 3 ? A1_SM_W0 : h < 6 ? A1_SM_W3 - 3 * WOB : -6 * WOB); }
#define A1_FRED "red.relaxed.gpu.global.add.u32"
#define A1_FLD "ld.acquire.gpu.global.u32"
#define ST_SLEEP 20
#define ST_SLEEP0 300
#define WO_LATE bar_done
#define A1_P0 2
#define A1_PW (kb - 2)
#define A1_FSPIN SPIN_MAX
#define A1_FSLEEP 40
#define A1_WOAT 6

template <int L>
__device__ __forceinline__ void a1_mainloop(float (&acc)[120], uint32_t sbase, uint32_t bars, int wg, int tile) {
    constexpr int layer = L; (void)layer;
    const uint64_t da0 = L ? make_desc(sbase + wg * 8192, 8192, 1024, 1) : make_desc(sbase + wg * 8192, 16, 1024, 1), db0 = make_desc(sbase + 16384, 1024, 256, 3);
#pragma unroll 1
    for (int t = 0;; t++) {
        const int st = t % A1_NST;
        mbar_wait(bars + 8 * st, (t / A1_NST) & 1);
        if (t == A1_SKEW && wg == 0) mbar_wait(bars + 160, 0);
        TSTAMP3(1 + t);
        wgmma_fence();
#pragma unroll
        for (int kk = 0; kk < 4; kk++) wgmma_n240<L, 1>(acc, da0 + (uint32_t)(st * (A1_STAGE / 16) + kk * (L ? 128 : 2)), db0 + (uint32_t)(st * (A1_STAGE / 16) + (kk >> 1) * (WQ_STAGE / 32) + (kk & 1) * 32), kk ? 1 : t);
        wgmma_commit();
        if (t == 9) break;
        if (t == A1_SKEW - 1 && wg == 0) wgmma_wait<0>(); else wgmma_wait<1>();
        if (t > 0 && (threadIdx.x & 127) == 0) {
            if (t != A1_SKEW || wg) mbar_arrive(bars + 8 * (A1_NST + (t - 1) % A1_NST));
            if (t == A1_SKEW - 1 && wg == 0) mbar_arrive(bars + 8 * (A1_NST + t % A1_NST));
        }
    }
}

__global__ void __launch_bounds__(A1_THREADS, 1) a1_kernel(const int layer, const bf16* __restrict__ x0, const unsigned char* __restrict__ wq, const unsigned char* __restrict__ wo,
                                                           float2* __restrict__ rsum, uint4* __restrict__ of, const __grid_constant__ CUtensorMap tmX,
                                                           const __grid_constant__ CUtensorMap tmR, const __grid_constant__ CUtensorMap tmX1, const __grid_constant__ TileTab tab) {
    extern __shared__ __align__(1024) unsigned char stg[];
    const uint32_t sbase = smem_u32(stg);
    const uint32_t bars = sbase + A1_SM_BAR;
    const uint32_t bar_stat = bars + 64, bar_kv = bars + 72, bar_rd = bars + 168;
    const uint32_t bar_wo = bars + 208, bar_done = bars + 216, bar_pv = bars + 224, bar_kvf = bars + 232, bar_f2 = bars + 248, bar_e2 = bars + 384, que = bars + 448;
    const int tid = threadIdx.x;
    const int w = __shfl_sync(~0u, tid >> 5, 0), wg = w >> 2;
    uint32_t smid, ns;
    asm volatile("mov.u32 %0, %smid;" : "=r"(smid));
    asm volatile("mov.u32 %0, %nsmid;" : "=r"(ns));
    const auto te = tab.e[ns == tab.ns ? smid : 132 + blockIdx.x];
    const int tile = te.tile, mb = te.mb, hg = te.hg;
    float2* rst = reinterpret_cast<float2*>(stg + A1_SM_RS) + 8;
    auto issue_w = [&](int it) { bulk_load(sbase + (it % A1_NST) * A1_STAGE + 16384, wq + te.woff + it * WQ_STAGE, WQ_STAGE, bars + 8 * (it % A1_NST)); };
    auto issue_x = [&](int it, int kb) {
        asm volatile("cp.async.bulk.tensor.5d.shared::cluster.global.mbarrier::complete_tx::bytes [%0], [%1, {%3, %3, %3, %4, %5}], [%2];"
                     ::"r"(sbase + (it % A1_NST) * A1_STAGE), "l"(&tmX), "r"(bars + 8 * (it % A1_NST)), "r"(0), "r"(mb), "r"(kb) : "memory");
    };
    if (w == 8 && tile < 128) {
        const bool one = elect();
        if (one) {
#pragma unroll
            for (int i = 0; i < A1_NST; i++) mbar_init(bars + 8 * i, 1);
            asm volatile("fence.mbarrier_init.release.cluster;" ::: "memory");
        }
        __syncwarp();
        asm volatile("bar.arrive 0, 384;" ::: "memory");
        if (one) {
#define PW asm volatile("griddepcontrol.wait;" ::: "memory");
            if (layer) { issue_w(0); PW issue_x(0, te.kb0); issue_x(1, te.kb0 + 1); }
            else { issue_x(0, te.kb0); issue_x(1, te.kb0 + 1); PW issue_w(0); }
            issue_w(1);
#pragma unroll
            for (int i = 0; i < A1_NST; i++) mbar_expect_tx(bars + 8 * i, A1_STAGE);
            asm volatile("griddepcontrol.launch_dependents;" ::: "memory");
#pragma unroll
            for (int kb = 2; kb < A1_P0; kb++) { issue_x(kb, te.kb0 + kb); issue_w(kb); }
            DBGC(34); DBGV(33, smid); DBGV(40, t_entry); DBGV(30, t_a); DBGV(31, t_b); DBGV(32, t_c); DBGV(38, t_d); DBGV(39, t_e);
        }
    }
    if (tile >= 128) { sm_idle(layer); return; }
    if (wg == 2) {
        if (w != 8) {
            if (tid == 320) { prefetch_tmap(&tmX); prefetch_tmap(&tmR); prefetch_tmap(&tmX1); }
            asm volatile("bar.sync 0, 384;" ::: "memory");
        }
        if (w == 9) {
            asm volatile("bar.arrive 3, 64;" ::: "memory");
            if (layer == 0) pdl_sync();
            float4 a[2] = {};
#pragma unroll
            for (int k = 0; k < 10; k++)
#pragma unroll
                for (int h = 0; h < 2; h++) {
                    const int c4 = min(tid - 288 + 32 * h, 59);
                    const float4 v = __ldcg(reinterpret_cast<const float4*>(g_csp + k * 1920 + hg * 80) + c4 + (c4 / 20) * 140);
                    a[h].x += v.x; a[h].y += v.y; a[h].z += v.z; a[h].w += v.w;
                }
#pragma unroll
            for (int h = 0; h < 2; h++)
#pragma unroll
                for (int k = 0; k < 4; k++) {
                    const float c = 0.5f * (k == 0 ? a[h].x : k == 1 ? a[h].y : k == 2 ? a[h].z : a[h].w), c1 = c - rbf(c), c2 = c1 - rbf(c1);
                    *reinterpret_cast<uint4*>(stg + A1_SM_XB + (4 * min(tid - 288 + 32 * h, 59) + k) * 16) = make_uint4(pack2(c, c1), pack2(c2, 0.f), 0u, 0u);
                }
            fence_async_smem();
            __syncwarp();
            if (tid == 288) mbar_arrive(bar_stat);
#pragma unroll 4
            for (int k = 0; k < 40; k++) asm volatile("st.global.v4.u32 [%0], {%1,%1,%1,%1};" ::"l"(of + (mb * 8 + hg) * 1280 + 32 * k + (tid - 288)), "r"(~0u) : "memory");
            asm volatile("fence.acq_rel.gpu;" ::: "memory");
            asm volatile("fence.proxy.async.global;" ::: "memory");
            __syncwarp();
            if (tid == 288) mbar_arrive(bar_done);
            TSTAMP1T(9, 288);
        } else if (w == 8) {
            asm volatile("bar.sync 3, 64;" ::: "memory");
            if (elect()) {
#pragma unroll 1
                for (int kb = A1_P0; kb < 10; kb++) {
                    if (kb < A1_NST) mbar_wait(bars + 8 * A1_PW, 0);
                    else {
                        mbar_wait(bars + 8 * (A1_NST + kb % A1_NST), ((kb / A1_NST) - 1) & 1);
                        if (layer && kb < 9) mbar_wait(bar_rd + 8 * (kb - A1_NST), 0);
                        mbar_expect_tx(bars + 8 * (kb % A1_NST), A1_STAGE);
                    }
                    issue_x(kb, kb < 5 ? kb + te.kb0 : kb - te.kb0); issue_w(kb);
                    if (kb == A1_WOAT) {
                        mbar_expect_tx(bar_wo, 8 * WOB);
                        bulk_load(sbase + A1_SM_W0, wo + hg * 8 * WOB, 2 * WOB, bar_wo);
                    }
                }
                TSTAMP1T(6, 256);
                mbar_wait(bars + 8 * (A1_NST + 3), 1);
                bulk_load(sbase + A1_SM_W3, wo + (hg * 8 + 3) * WOB, 3 * WOB, bar_wo);
            }
            __syncwarp();
        } else {
            const int j = tid - 320;
            const uint32_t tag = ld_epoch();
            if (tid == 352) sm_started(layer);
            if (layer == 0) {
                const uint4* src = reinterpret_cast<const uint4*>(x0 + (size_t)(mb * 128 + hg * 16 + (j >> 2)) * DM);
                uint4 v[20];
#pragma unroll
                for (int k = 0; k < 20; k++) v[k] = __ldg(src + (j & 3) + 4 * k);
                const float p0 = __uint_as_float(__shfl_sync(~0u, v[0].x, j & 28) << 16);
                float s[2] = {0.f, 0.f}, q[2] = {0.f, 0.f};
#pragma unroll
                for (int k = 0; k < 20; k++) {
                    const uint32_t w[4] = {v[k].x, v[k].y, v[k].z, v[k].w};
#pragma unroll
                    for (int i = 0; i < 4; i++) {
                        const float a = __uint_as_float(w[i] << 16) - p0, b = __uint_as_float(w[i] & 0xffff0000u) - p0;
                        s[0] += a; s[1] += b; q[0] = fmaf(a, a, q[0]); q[1] = fmaf(b, b, q[1]);
                    }
                }
                float s0 = s[0] + s[1], q0 = q[0] + q[1];
#pragma unroll
                for (int o = 1; o <= 2; o <<= 1) { s0 += __shfl_xor_sync(~0u, s0, o); q0 += __shfl_xor_sync(~0u, q0, o); }
                if ((j & 3) == 0) {
                    const float d = s0 * (1.0f / DM);
                    const uint32_t ms = pack2(p0 + d, sqrt_apx(rbf(rbf(fmaxf(fmaf(-d, d, q0 * (1.0f / DM)), 0.f)) + 1e-5f)));
                    asm volatile("st.global.cg.u64 [%0], %1;" ::"l"(g_rstat + mb * 128 + (j & 4) * 16 + hg * 8 + (j >> 3)), "l"(tagw(ms, tag)) : "memory");
                    g_piv[mb * 128 + hg * 16 + ((j >> 2) & 8) + (j & 4) + ((j >> 3) & 3)] = __ushort_as_bfloat16((unsigned short)ms);
                }
            }
            float o[4];
            int row;
            if (layer == 0) {
                ulonglong2 v;
#pragma unroll 1
                for (int it = 0; it < SPIN_MAX; it++) {
                    v = ld_tag2(reinterpret_cast<const ulonglong2*>(g_rstat + mb * 128) + j);
                    if (tag_ok(v, tag)) break;
                    __nanosleep(100);
                }
                o[0] = __uint_as_float((uint32_t)v.x << 16); o[1] = rcp_apx(__uint_as_float((uint32_t)v.x & 0xffff0000u));
                o[2] = __uint_as_float((uint32_t)v.y << 16); o[3] = rcp_apx(__uint_as_float((uint32_t)v.y & 0xffff0000u));
                row = 2 * j;
            } else {
                const int ch = j & 7, kg = (j >> 3) & 3;
                const unsigned char* src = stg + (j >> 5) * 8192 + (hg & 3) * 2048;
                float s[8], q[8], p0[8];
#pragma unroll
                for (int i = 0; i < 8; i++) { s[i] = 0.f; q[i] = 0.f; }
#pragma unroll 1
                for (int it = 0; it < 5; it++) {
                    uint4 v[4];
                    mbar_wait(bars + 8 * (it % A1_NST), it / A1_NST);
#pragma unroll
                    for (int k = 0; k < 4; k++) v[k] = *reinterpret_cast<const uint4*>(src + (it % A1_NST) * A1_STAGE + (4 * k + kg) * 128 + ((ch ^ ((4 * k + kg) & 7)) << 4));
                    if (it == 0) {
                        const uint4 pv = *reinterpret_cast<const uint4*>(src + (ch << 4));
                        const uint32_t w[4] = {pv.x, pv.y, pv.z, pv.w};
#pragma unroll
                        for (int i = 0; i < 4; i++) { p0[2 * i] = __uint_as_float(w[i] << 16); p0[2 * i + 1] = __uint_as_float(w[i] & 0xffff0000u); }
                    }
                    asm volatile("" :: "r"(v[0].x), "r"(v[1].x), "r"(v[2].x), "r"(v[3].x), "f"(p0[0]) : "memory");
                    __syncwarp();
                    if ((tid & 31) == 0) mbar_arrive(bar_rd + 8 * it);
#pragma unroll
                    for (int k = 0; k < 4; k++) {
                        const uint32_t w[4] = {v[k].x, v[k].y, v[k].z, v[k].w};
#pragma unroll
                        for (int i = 0; i < 4; i++) {
                            const float a = __uint_as_float(w[i] << 16) - p0[2 * i], b = __uint_as_float(w[i] & 0xffff0000u) - p0[2 * i + 1];
                            s[2 * i] += a; s[2 * i + 1] += b; q[2 * i] = fmaf(a, a, q[2 * i]); q[2 * i + 1] = fmaf(b, b, q[2 * i + 1]);
                        }
                    }
                }
#pragma unroll
                for (int i = 0; i < 4; i++) {
                    const bool up = kg & 2;
                    const float ss = __shfl_xor_sync(~0u, up ? s[i] : s[i + 4], 16), qq = __shfl_xor_sync(~0u, up ? q[i] : q[i + 4], 16);
                    s[i] = (up ? s[i + 4] : s[i]) + ss; q[i] = (up ? q[i + 4] : q[i]) + qq; p0[i] = up ? p0[i + 4] : p0[i];
                }
#pragma unroll
                for (int i = 0; i < 2; i++) {
                    const bool up = kg & 1;
                    const float ss = __shfl_xor_sync(~0u, up ? s[i] : s[i + 2], 8), qq = __shfl_xor_sync(~0u, up ? q[i] : q[i + 2], 8);
                    s[i] = (up ? s[i + 2] : s[i]) + ss; q[i] = (up ? q[i + 2] : q[i]) + qq; p0[i] = up ? p0[i + 2] : p0[i];
                }
                uint4* gp = g_halo + 86016 + mb * 512 + j;
                const float d0 = s[0] * (1.0f / 80.0f), d1 = s[1] * (1.0f / 80.0f);
                asm volatile("st.relaxed.gpu.global.v4.f32 [%0], {%1,%2,%3,%4};" ::"l"(gp + hg * 64), "f"(p0[0] + d0), "f"(fmaxf(fmaf(-d0, s[0], q[0]), 0.f)), "f"(p0[1] + d1), "f"(fmaxf(fmaf(-d1, s[1], q[1]), 0.f)) : "memory");
                __nanosleep(ST_SLEEP0);
                uint32_t pw[8][4], todo = 0xff;
#pragma unroll 1
                for (int it = 0; it < SPIN_MAX; it++) {
#pragma unroll
                    for (int k = 0; k < 8; k++)
                        if (todo >> k & 1) asm volatile("ld.relaxed.gpu.global.v4.u32 {%0,%1,%2,%3}, [%4];" : "=r"(pw[k][0]), "=r"(pw[k][1]), "=r"(pw[k][2]), "=r"(pw[k][3]) : "l"(gp + k * 64) : "memory");
#pragma unroll
                    for (int k = 0; k < 8; k++)
                        if (__all_sync(~0u, pw[k][0] != ~0u && pw[k][1] != ~0u && pw[k][2] != ~0u && pw[k][3] != ~0u)) todo &= ~(1u << k);
                    if (!todo) break;
                    __nanosleep(ST_SLEEP);
                }
#pragma unroll
                for (int r = 0; r < 2; r++) {
                    float mean = 0.f, m2 = 0.f;
#pragma unroll
                    for (int k = 0; k < 8; k++) mean += __uint_as_float(pw[k][2 * r]);
                    mean *= 0.125f;
#pragma unroll
                    for (int k = 0; k < 8; k++) {
                        const float dm = __uint_as_float(pw[k][2 * r]) - mean;
                        m2 += fmaf(80.0f * dm, dm, __uint_as_float(pw[k][2 * r + 1]));
                    }
                    o[2 * r] = rbf(mean);
                    o[2 * r + 1] = rcp_apx(rbf(sqrt_apx(rbf(rbf(m2 * (1.0f / DM)) + 1e-5f))));
                }
                row = (j >> 5) * 64 + (j & 7) * 8 + ((j >> 3) & 3) * 2;
                if (hg == 0) *reinterpret_cast<uint32_t*>(g_piv + SEQ + mb * 128 + 2 * (row & 60) + 4 * (row >> 6) + (row & 3)) = __byte_perm(__float_as_uint(o[0]), __float_as_uint(o[2]), 0x7632);
            }
#pragma unroll
            for (int r = 0; r < 2; r++)
                *reinterpret_cast<uint4*>(stg + A1_SM_XA + (row + r) * 16) = make_uint4(__byte_perm(__float_as_uint(-o[2 * r]), 0, 0x3232), __float_as_uint(-o[2 * r]) >> 16, 0u, 0u);
            *reinterpret_cast<float4*>(rst + row + (row >> 6) * 8) = make_float4(o[0], o[1], o[2], o[3]);
            fence_async_smem();
            TSTAMP1T(7, 320);
            if (tid == 320) DBGC(44);
            __syncwarp();
            if ((tid & 31) == 0) mbar_arrive(bar_stat);
        }
        if (tid == 320) DBGCAL(0);
        if (tid == 352) {
            mbar_wait(WO_LATE, 0);
            mbar_wait(bar_done, 0);
            bulk_load(sbase, wo + (hg * 8 + 6) * WOB, 2 * WOB, bar_wo);
            bulk_load(sbase + A1_SM_W0 + 2 * WOB, wo + (hg * 8 + 2) * WOB, WOB, bar_wo);
        }
        if (w < 10) {
            const int cw = w - 8;
            const uint32_t* fl = reinterpret_cast<const uint32_t*>(rsum + 2 * SEQ) + (((layer * 16 + mb) * 2 + cw) * 8 + (tid & 7)) * FSTR;
            const unsigned char* src = reinterpret_cast<const unsigned char*>(of) + mb * 163840 + cw * 10240 + (tid & 7) * 20480;
            const uint32_t sl = sbase + (cw ? A1_SM_A1 : A1_SM_A0);
            mbar_wait(cw ? bar_done : bar_kvf, 0);
            if ((tid & 31) == 0) {
                mbar_expect_tx(bar_f2 + 64 * cw + 64, 10240);
                tma_load_3d(sl + 51200, &tmR, layer ? 0 : hg * 80, layer ? hg * 80 : mb * 64, layer ? mb * 2 + cw : cw, bar_f2 + 64 * cw + 64);
            }
            __syncwarp();
            uint32_t pend = 0xffu & ~(1u << hg), v = 0;
            const uint32_t bo = wo_off((tid & 7) + ((tid & 7) < hg)) >> 4, lt = (1u << (tid & 31)) - 1;
#pragma unroll 1
            for (int it = 0; pend && it < 2 * SPIN_MAX; it++) {
                if (v != 4 && (pend >> (tid & 31) & 1)) asm volatile(A1_FLD " %0, [%1];" : "=r"(v) : "l"(fl) : "memory");
                uint32_t fr;
                asm volatile("{\n.reg .pred p;\nmbarrier.test_wait.parity.shared::cta.b64 p, [%1], 0;\nselp.b32 %0, 1, 0, p;\n}" : "=r"(fr) : "r"(bar_e2 + 16 * cw + (tid & 1) * 8) : "memory");
                fr = __ballot_sync(~0u, fr);
                uint32_t m = __ballot_sync(~0u, v == 4 || it >= A1_FSPIN) & pend;
                const int q = 8 - __popc(pend) + __popc(m & lt);
                m &= __ballot_sync(~0u, q < ((fr & 2) ? 8 : (fr & 1) ? 7 : 5));
                pend ^= m;
                if (m >> (tid & 31) & 1) DBGC(12 + cw * 8 + (tid & 7));
                if (!m) __nanosleep(A1_FSLEEP);
                else asm volatile("fence.proxy.async.global;" ::: "memory");
                if (m >> (tid & 31) & 1) {
                    bulk_load(q == 7 && !cw ? sbase + A1_SM_W0 : sl + (q < 6 ? q : q - 6) * 10240, src, 10240, bar_f2 + 64 * cw + 8 * q);
                    asm volatile("st.shared.u32 [%0], %1;" ::"r"(que + 32 * cw + 4 * q), "r"(bo) : "memory");
                    mbar_expect_tx(bar_f2 + 64 * cw + 8 * q, 10240);
                    DBGC(44 + cw * 8 + q);
                }
                __syncwarp();
            }
        }
    } else {
        if (tid == 0) {
            mbar_init(bar_stat, 3);
#pragma unroll
            for (int i = 0; i < 8; i++) mbar_init(bar_kv + 8 * i, 1);
            mbar_init(bars + 144, 1);
            mbar_init(bars + 160, 1);
#pragma unroll
            for (int i = 0; i < 5; i++) mbar_init(bar_rd + 8 * i, 2);
            asm volatile("fence.mbarrier_init.release.cluster;" ::: "memory");
        } else if (tid == 32) {
            mbar_init(bar_wo, 1); mbar_init(bar_done, 3); mbar_init(bar_pv, 4); mbar_init(bar_kvf, 8); mbar_init(bars + 240, 4);
#pragma unroll
            for (int i = 0; i < 4; i++) { mbar_init(bar_e2 + 8 * i, i == 1 ? 2 : 1); mbar_init(bars + 8 * (A1_NST + i), 2); }
            asm volatile("fence.mbarrier_init.release.cluster;" ::: "memory");
        } else if (tid == 64) {
#pragma unroll
            for (int i = 1; i <= 16; i++) mbar_init(bar_f2 + 8 * i, 1);
            asm volatile("fence.mbarrier_init.release.cluster;" ::: "memory");
        }
        asm volatile("bar.sync 0, 384;" ::: "memory");
        SPAN(1 + 4 * layer, 0);
        constexpr int on = 1;
        float acc[120];
        const int lane = tid & 31, warp = w & 7, g = lane >> 2, t = lane & 3;
        if (on) {
            SPAN(1 + 4 * layer, 1);
            TSTAMP1(0);
            if (threadIdx.x == 0) { GSTAMP(g_tim1, 15); }
            TSTAMP3(0);
            if (tid == 0) TSTAMP2(0);
            TSTAMP4(0);
            if (tid == 0) DBGC(60);
            if (layer == 0) a1_mainloop<0>(acc, sbase, bars, wg, tile); else a1_mainloop<1>(acc, sbase, bars, wg, tile);
            uint32_t ok;
            asm volatile("{\n.reg .pred p;\nmbarrier.test_wait.parity.shared::cta.b64 p, [%1], 0;\nselp.b32 %0, 1, 0, p;\n}" : "=r"(ok) : "r"(bar_stat) : "memory");
            if (tid == 128 && !ok) mbar_arrive(bars + 160);
            __syncwarp();
            mbar_wait(bar_stat, 0);
            wgmma_fence();
            wgmma_n240<0, 0>(acc, make_desc(sbase + A1_SM_XA + wg * 1024, 0, 128, 0), make_desc(sbase + A1_SM_XB, 0, 128, 0), 1);
            wgmma_commit();
            if (tid == 128 && ok) mbar_arrive(bars + 160);
            mbar_wait(bars + 8 * (A1_NST + 3), 1);
        }
        const float2* rw = rst + 16 * warp + 8 * wg;
        const float rb0 = rw[g + 8].y, ra = rw[g].y * 0.22360679774997896f, rb = rb0 * 0.22360679774997896f;
        wgmma_wait<0>();
        if ((tid & 127) == 0) mbar_arrive(bar_done);
        TSTAMP1(2);
        TSTAMP1T(13, 224);
        if ((tid & 127) == 0) DBGC(62 - wg);
        uint32_t f[2][30];
#pragma unroll
        for (int j = 10; j < 30; j++) f[1][j] = pack2(acc[4 * j + 2], acc[4 * j + 3]);
        if ((warp & 3) == 3) {
            uint4* hout = g_halo + (((layer * 16 + mb) * 8 + hg) * 2 + wg) * 168;
#pragma unroll
            for (int j = 0; j < 20; j += 4)
                asm volatile("st.relaxed.gpu.global.v4.u32 [%0], {%1,%2,%3,%4};" ::"l"(hout + 8 * j + lane), "r"(f[1][10 + j]), "r"(f[1][11 + j]), "r"(f[1][12 + j]), "r"(f[1][13 + j]) : "memory");
            if (t == 0) asm volatile("st.relaxed.gpu.global.f32 [%0], %1;" ::"l"(reinterpret_cast<float*>(hout + 160) + g), "f"(rb0) : "memory");
        }
        TSTAMP1T(12, 224);
        const uint32_t kvw = sbase + A1_SM_KV + (16 * warp + 8 * wg) * A1_KVP;
        const uint32_t mrow = kvw + (lane & 7) * A1_KVP + (lane >> 3) * 16;
#pragma unroll
        for (int j = 0; j < 20; j += 4) stsm_x4(mrow + 16 * A1_KVP + 16 * j, f[1][10 + j], f[1][11 + j], f[1][12 + j], f[1][13 + j]);
        __syncwarp();
        if (lane == 0 && (warp & 3) != 3) mbar_arrive(bar_kv + 8 * (warp + 1));
#pragma unroll
        for (int j = 0; j < 30; j++) f[0][j] = pack2(acc[4 * j], acc[4 * j + 1]);
        stsm_x4(mrow + 8 * A1_KVP + 160, f[0][20], f[0][21], f[0][22], f[0][23]);
        stsm_x4(mrow + 8 * A1_KVP + 224, f[0][24], f[0][25], f[0][26], f[0][27]);
        asm volatile("stmatrix.sync.aligned.m8n8.x2.shared.b16 [%0], {%1,%2};" ::"r"(mrow + 8 * A1_KVP + 288), "r"(f[0][28]), "r"(f[0][29]) : "memory");
#pragma unroll
        for (int j = 0; j < 10; j++) f[1][j] = pack2(acc[4 * j + 2], acc[4 * j + 3]);
        __syncwarp();
        uint32_t vb[10][2], vp[12], kp[12];
#pragma unroll
        for (int j = 0; j < 10; j += 2) ldsm_x4_t(&vb[j][0], kvw + (8 + (lane & 15)) * A1_KVP + 160 + (lane >> 4) * 16 + 16 * j);
        const bool up0 = 2 * t > g, up1 = 2 * t + 1 > g, edge = (mb | (warp & 3)) == 0;
        float rk[4];
        auto above = [&]() {
            mbar_wait(bar_kv + 8 * warp, 0);
#pragma unroll
            for (int j = 0; j < 12; j += 4) ldsm_x4(&kp[j], mrow + 16 * j);
            rk[0] = rw[2 * t - (up0 ? 8 : 0)].y; rk[1] = rw[2 * t + 1 - (up1 ? 8 : 0)].y;
#pragma unroll
            for (int j = 0; j < 12; j += 4) ldsm_x4_t(&vp[j], mrow + 160 + 16 * j - (j == 8 ? (lane & 16) * 2 : 0));
            __syncwarp();
            if (lane == 0) mbar_arrive(bar_kvf);
        };
        auto halo = [&]() {
            if (lane == 0) mbar_arrive(bar_kvf);
            const uint4* hin = g_halo + (((layer * 16 + mb - 1) * 8 + hg) * 2 + wg) * 168;
            uint32_t hv[22] = {};
            rk[0] = rw[2 * t].y; rk[1] = rw[2 * t + 1].y;
            if (mb > 0) {
#pragma unroll 1
                for (int it = 0; it < SPIN_MAX; it++) {
#pragma unroll
                    for (int k = 0; k < 20; k += 4)
                        asm volatile("ld.relaxed.gpu.global.v4.u32 {%0,%1,%2,%3}, [%4];" : "=r"(hv[k]), "=r"(hv[k + 1]), "=r"(hv[k + 2]), "=r"(hv[k + 3]) : "l"(hin + 8 * k + lane) : "memory");
                    asm volatile("ld.relaxed.gpu.global.v2.u32 {%0,%1}, [%2];" : "=r"(hv[20]), "=r"(hv[21]) : "l"(reinterpret_cast<const uint2*>(hin + 160) + t) : "memory");
                    uint32_t m = max(hv[20], hv[21]);
#pragma unroll
                    for (int k = 0; k < 20; k += 2) m = __vimax3_u32(m, hv[k], hv[k + 1]);
                    if (!__any_sync(~0u, m == ~0u)) break;
                }
            }
            if (tid == 0) mbar_arrive(bars + 144);
            if (lane == 0) DBGC(52 - 16 * wg);
#pragma unroll
            for (int j = 0; j < 10; j++) {
                kp[j] = hv[j];
                asm volatile("movmatrix.sync.aligned.m8n8.trans.b16 %0, %1;" : "=r"(vp[j]) : "r"(hv[10 + j]));
            }
            if (up0) rk[0] = __uint_as_float(hv[20]);
            if (up1) rk[1] = __uint_as_float(hv[21]);
        };
        rk[2] = rw[2 * t + (up0 ? 0 : 8)].y; rk[3] = rw[2 * t + 1 + (up1 ? 0 : 8)].y;
        uint32_t qs[4][2];
#pragma unroll
        for (int h = 0; h < 4; h++) {
            qs[h][0] = (t >> 1) == (h & 1) ? f[0][5 * (h >> 1) + 2] : 0u; qs[h][1] = (t >> 1) == (h & 1) ? f[1][5 * (h >> 1) + 2] : 0u;
            asm volatile("" : "+r"(qs[h][0]), "+r"(qs[h][1]));
        }
#pragma unroll
        for (int j = 0; j < 10; j++) asm volatile("" : "+r"(f[0][j]), "+r"(f[1][j]), "+r"(f[0][10 + j]));
        if (warp & 3) above(); else if (wg) halo();
        TSTAMP1T(10, 64);
        float sc[4][3][4];
#pragma unroll
        for (int h = 0; h < 4; h++) {
            const int jb = 5 * (h >> 1) + 3 * (h & 1), js = 5 * (h >> 1) + 2;
#pragma unroll
            for (int nt = 1; nt < 3; nt++) {
#pragma unroll
                for (int e = 0; e < 4; e++) sc[h][nt][e] = 0.f;
                mma_bf16(sc[h][nt], f[0][jb], f[1][jb], f[0][jb + 1], f[1][jb + 1], f[nt - 1][10 + jb], f[nt - 1][11 + jb]);
                mma_bf16_k8(sc[h][nt], qs[h][0], qs[h][1], f[nt - 1][10 + js]);
            }
        }
        if (tid == 128) mbar_arrive(bars + 240);
        if (warp == 0) halo();
        TSTAMP1(8);
#pragma unroll
        for (int h = 0; h < 4; h++) {
            const int jb = 5 * (h >> 1) + 3 * (h & 1), js = 5 * (h >> 1) + 2;
#pragma unroll
            for (int e = 0; e < 4; e++) sc[h][0][e] = 0.f;
            mma_bf16(sc[h][0], f[0][jb], f[1][jb], f[0][jb + 1], f[1][jb + 1], kp[jb], kp[jb + 1]);
            mma_bf16_k8(sc[h][0], qs[h][0], qs[h][1], kp[js]);
        }
        if (warp > 4) { __syncwarp(); if (lane == 0) mbar_arrive(bars + 240); }
        TSTAMP1T(3, 64);
        float p[4][4], sum[4][2];
        uint32_t lg[4][2], mx[4];
        const float rl[4] = {rk[0] * ra, rk[1] * ra, rk[2] * rb, rk[3] * rb};
        auto max2 = [](uint32_t a, uint32_t b) { uint32_t r; asm("max.bf16x2 %0, %1, %2;" : "=r"(r) : "r"(a), "r"(b)); return r; };
#pragma unroll
        for (int h = 0; h < 4; h++) {
            lg[h][0] = pack2((up0 ? sc[h][0][0] : sc[h][1][0]) * rl[0], (up0 ? sc[h][1][2] : sc[h][2][2]) * rl[2]);
            lg[h][1] = pack2((up1 ? sc[h][0][1] : sc[h][1][1]) * rl[1], (up1 ? sc[h][1][3] : sc[h][2][3]) * rl[3]);
            if (edge) {
                if (up0) lg[h][0] = __byte_perm(lg[h][0], 0xce6eu, 0x3254);
                if (up1) lg[h][1] = __byte_perm(lg[h][1], 0xce6eu, 0x3254);
            }
            mx[h] = max2(lg[h][0], lg[h][1]);
        }
#pragma unroll
        for (int o = 1; o <= 2; o <<= 1)
#pragma unroll
            for (int h = 0; h < 4; h++) mx[h] = max2(mx[h], __shfl_xor_sync(~0u, mx[h], o));
#pragma unroll
        for (int h = 0; h < 4; h++)
#pragma unroll
            for (int r = 0; r < 2; r++) {
                const float m = __uint_as_float(r ? mx[h] & 0xffff0000u : mx[h] << 16);
#pragma unroll
                for (int e = 0; e < 2; e++)
                    asm("ex2.approx.ftz.f32 %0, %1;" : "=f"(p[h][2 * r + e]) : "f"((__uint_as_float(r ? lg[h][e] & 0xffff0000u : lg[h][e] << 16) - m) * 1.4426950408889634f));
                sum[h][r] = p[h][2 * r] + p[h][2 * r + 1];
            }
#pragma unroll
        for (int o = 1; o <= 2; o <<= 1)
#pragma unroll
            for (int h = 0; h < 4; h++)
#pragma unroll
                for (int r = 0; r < 2; r++) sum[h][r] += __shfl_xor_sync(~0u, sum[h][r], o);
        TSTAMP1T(5, 64);
        const uint32_t mu = (up0 ? 0xffffu : 0u) | (up1 ? 0xffff0000u : 0u);
        uint32_t ob[10][2];
#pragma unroll
        for (int P = 0; P < 2; P++) {
            float os[2][4];
#pragma unroll
            for (int e = 0; e < 2; e++) {
                const int h = 2 * P + e;
                const float i0 = rcp_apx(sum[h][0]), i1 = rcp_apx(sum[h][1]);
                const uint32_t w0 = pack2(p[h][0] * rk[0] * i0, p[h][1] * rk[1] * i0), w1 = pack2(p[h][2] * rk[2] * i1, p[h][3] * rk[3] * i1);
#pragma unroll
                for (int dt = 0; dt < 3; dt++) {
                    const int j = 5 * P + (dt < 2 ? 3 * e + dt : 2);
                    float o[4] = {0.f, 0.f, 0.f, 0.f};
                    mma_bf16(o, w0 & ~mu, w1 & mu, 0u, w1 & ~mu, vb[j][0], vb[j][1]);
                    mma_bf16_k8(o, w0 & mu, 0u, vp[j]);
                    if (dt < 2) { ob[j][0] = pack2(o[0], o[1]); ob[j][1] = pack2(o[2], o[3]); }
                    else { os[e][0] = o[0]; os[e][1] = o[1]; os[e][2] = o[2]; os[e][3] = o[3]; }
                }
            }
#pragma unroll
            for (int k = 0; k < 4; k++) os[0][k] = t < 2 ? os[0][k] : os[1][k];
            ob[5 * P + 2][0] = pack2(os[0][0], os[0][1]); ob[5 * P + 2][1] = pack2(os[0][2], os[0][3]);
        }
        const uint32_t sl = sbase + (wg ? A1_SM_A1 : A1_SM_A0);
        const uint32_t o0 = (warp & 3) * 2048 + g * 64 + ((t ^ (g >> 1)) << 4), o1 = 8192 + (warp & 3) * 512 + g * 32 + ((t ^ ((g >> 2) << 1)) << 3);
        mbar_wait(bar_done, 0);
        if (wg == 0) mbar_wait(bar_kvf, 0);
#pragma unroll
        for (int h = 0; h < 2; h++) {
            asm volatile("st.shared.v4.u32 [%0], {%1,%2,%3,%4};" ::"r"(sl + o0 + h * 1024), "r"(ob[0][h]), "r"(ob[1][h]), "r"(ob[2][h]), "r"(ob[3][h]) : "memory");
            asm volatile("st.shared.v4.u32 [%0], {%1,%2,%3,%4};" ::"r"(sl + o0 + h * 1024 + 512), "r"(ob[4][h]), "r"(ob[5][h]), "r"(ob[6][h]), "r"(ob[7][h]) : "memory");
            asm volatile("st.shared.v2.u32 [%0], {%1,%2};" ::"r"(sl + o1 + h * 256), "r"(ob[8][h]), "r"(ob[9][h]) : "memory");
        }
        fence_async_smem();
        __syncwarp();
        TSTAMP1T(4, 64);
        TSTAMP1(1);
        TSTAMP2(1);
        const unsigned char* ot = reinterpret_cast<const unsigned char*>(of) + mb * 163840 + wg * 10240;
        if (lane == 0) {
            asm volatile("cp.async.bulk.global.shared::cta.bulk_group [%0], [%1], 2048;" ::"l"(ot + hg * 20480 + (warp & 3) * 2048), "r"(sl + (warp & 3) * 2048) : "memory");
            asm volatile("cp.async.bulk.global.shared::cta.bulk_group [%0], [%1], 512;" ::"l"(ot + hg * 20480 + 8192 + (warp & 3) * 512), "r"(sl + 8192 + (warp & 3) * 512) : "memory");
            asm volatile("cp.async.bulk.commit_group;" ::: "memory");
            if (wg == 0) mbar_arrive(bar_pv);
            asm volatile("cp.async.bulk.wait_group 0;" ::: "memory");
            asm volatile(A1_FRED " [%0], 1;" ::"l"(reinterpret_cast<uint32_t*>(rsum + 2 * SEQ) + (((layer * 16 + mb) * 2 + wg) * 8 + hg) * FSTR) : "memory");
            DBGC(4 + warp);
        }
        TSTAMP4(11);
        float ac2[40];
        const uint64_t db0 = make_desc(sbase, 1024, 256, 3), db1 = make_desc(sbase + 10240, 512, 256, 3), da0 = make_desc(sl, 16, 1024, 2), da1 = make_desc(sl + 8192, 16, 256, 3);
        const uint32_t o7 = wg ? 640 : (A1_SM_W0 - A1_SM_A0) >> 4;
        const uint32_t trow = ((lane & 7) + 8 * (lane >> 4)) * 128 + (((2 * (warp & 3) + ((lane >> 3) & 1)) ^ (lane & 7)) << 4);
        uint32_t xr[10][2];
        mbar_wait(bar_f2 + 64 * wg + 64, 0);
        if (layer == 0) {
#pragma unroll
            for (int j = 0; j < 10; j += 2) ldsm_x4(&xr[j][0], sl + 51200 + (16 * (warp & 3) + (lane & 15)) * 160 + (lane >> 4) * 16 + 16 * j);
        } else {
#pragma unroll
            for (int j = 0; j < 10; j += 2) ldsm_x4_t(&xr[j][0], sl + 51200 + trow + 1024 * j);
        }
        const uint32_t ri = __shfl_sync(~0u, layer * SEQ + (wg * 2 + ((g >> 1) & 1)) * 512 + (mb * 16 + 4 * (warp & 3) + (g >> 2)) * 2 + (g & 1), lane);
        mbar_wait(bar_wo, 0);
        if (wg) mbar_wait(bar_pv, 0);
        if (wg) asm volatile("bar.sync 2, 128;" ::: "memory"); else asm volatile("bar.sync 1, 128;" ::: "memory");
        TSTAMP2(2);
#pragma unroll
        for (int q = 0; q < 8; q++) {
            uint32_t bo = wo_off(0) >> 4;
            if (q) {
                mbar_wait(bar_f2 + 64 * wg + 8 * q, 0);
                asm volatile("ld.shared.u32 %0, [%1];" : "=r"(bo) : "r"(que + 32 * wg + 4 * q) : "memory");
                bo = __shfl_sync(~0u, bo, 0);
                TSTAMP4(q);
                if (q == 1 && (tid & 127) == 0) DBGC(29 + 8 * wg);
            }
            wgmma_fence();
#pragma unroll
            for (int j = 0; j < 5; j++) wgmma_n80(ac2, (j < 4 ? da0 : da1) + (q == 7 ? o7 : 0u) + (uint64_t)((q < 6 ? q * 640 : 0) + (j & 2) * 16 + (j & 1) * 2), (j < 4 ? db0 : db1) + bo + (uint64_t)((j & 2) * 160 + (j & 1) * 32), j || q);
            wgmma_commit();
            if (q == 0) {
                wgmma_wait<0>();
                if ((tid & 127) == 0) { mbar_arrive(bar_e2 + 16 * wg); mbar_arrive(bar_e2 + 8); }
            }
            if (q == 2 && wg) {
                wgmma_wait<1>();
                if (tid == 128) mbar_arrive(bar_e2 + 24);
            }
        }
        if ((tid & 127) == 0) DBGC(28 + wg * 8 + 7);
        TSTAMP2(3);
        wgmma_wait<0>();
        TSTAMP2(4);
        if (__any_sync(~0u, ac2[0] != ac2[0] || ac2[2] != ac2[2])) {
#pragma unroll
            for (int i = 0; i < 40; i++) ac2[i] = 0.f;
            uint32_t a[20], an[20];
            auto lda = [&](uint32_t (&r)[20], int h) {
#pragma unroll
                for (int u = 0; u < 4; u++)
                    asm volatile("ld.relaxed.gpu.global.v4.u32 {%0,%1,%2,%3}, [%4];" : "=r"(r[4 * u]), "=r"(r[4 * u + 1]), "=r"(r[4 * u + 2]), "=r"(r[4 * u + 3]) : "l"(ot + h * 20480 + o0 + u * 512) : "memory");
#pragma unroll
                for (int u = 0; u < 2; u++)
                    asm volatile("ld.relaxed.gpu.global.v2.u32 {%0,%1}, [%2];" : "=r"(r[16 + 2 * u]), "=r"(r[17 + 2 * u]) : "l"(ot + h * 20480 + o1 + u * 256) : "memory");
            };
            lda(an, 0);
#pragma unroll 5
            for (int k = lane; k < WOB / 16; k += 32)
                reinterpret_cast<uint4*>(stg + (sl - sbase))[k] = __ldcg(reinterpret_cast<const uint4*>(wo + hg * 8 * WOB) + k);
            __syncwarp();
#pragma unroll 1
            for (int h = 0; h < 8; h++) {
#pragma unroll 1
                for (int it = 0; it < SPIN_MAX; it++) {
                    uint32_t m = 0;
#pragma unroll
                    for (int k = 0; k < 20; k += 2) m = __vimax3_u32(m, an[k], an[k + 1]);
                    if (!__any_sync(~0u, m == ~0u)) break;
                    lda(an, h);
                }
#pragma unroll
                for (int k = 0; k < 20; k++) a[k] = an[k];
                lda(an, min(h + 1, 7));
                const uint32_t bp = h == hg ? sl : sbase + wo_off(h + (h < hg));
                const int r0 = 8 * ((lane & 7) >> 1) + 2 * (lane >> 3) + (lane & 1), r2 = 4 * ((lane & 7) >> 1) + 2 * ((lane >> 3) & 1) + (lane & 1);
#pragma unroll
                for (int n = 0; n < 10; n++) {
                    uint32_t b[12];
                    ldsm_x4_t(b, bp + (n >> 1) * 1024 + r0 * 32 + (((n ^ (r0 >> 2)) & 1) << 4));
                    ldsm_x4_t(b + 4, bp + 5120 + (n >> 1) * 1024 + r0 * 32 + (((n ^ (r0 >> 2)) & 1) << 4));
                    ldsm_x4_t(b + 8, bp + 10240 + (n >> 1) * 512 + r2 * 32 + (((n ^ (r2 >> 2)) & 1) << 4));
                    mma_bf16(ac2 + 4 * n, a[0], a[8], a[1], a[9], b[0], b[1]); mma_bf16(ac2 + 4 * n, a[2], a[10], a[3], a[11], b[2], b[3]);
                    mma_bf16(ac2 + 4 * n, a[4], a[12], a[5], a[13], b[4], b[5]); mma_bf16(ac2 + 4 * n, a[6], a[14], a[7], a[15], b[6], b[7]);
                    mma_bf16(ac2 + 4 * n, a[16], a[18], a[17], a[19], b[8], b[9]);
                }
            }
        }
#pragma unroll
        for (int j = 0; j < 10; j++)
#pragma unroll
            for (int hh = 0; hh < 2; hh++) {
                const uint32_t a = pack2(ac2[4 * j + 2 * hh], ac2[4 * j + 2 * hh + 1]);
                const __nv_bfloat162 r = __hadd2_rn(*reinterpret_cast<const __nv_bfloat162*>(&xr[j][hh]), *reinterpret_cast<const __nv_bfloat162*>(&a));
                xr[j][hh] = *reinterpret_cast<const uint32_t*>(&r);
            }
        const uint32_t so = sl + 30720;
#pragma unroll
        for (int j = 0; j < 10; j += 2) stsm_x4_t(so + trow + 1024 * j, xr[j][0], xr[j][1], xr[j + 1][0], xr[j + 1][1]);
        fence_async_smem();
        if (wg) asm volatile("bar.sync 2, 128;" ::: "memory"); else asm volatile("bar.sync 1, 128;" ::: "memory");
        TSTAMP2(5);
        if ((tid & 127) == 0) {
            asm volatile("cp.async.bulk.tensor.2d.global.shared::cta.bulk_group [%0, {%1, %2}], [%3];" ::"l"(&tmX1), "r"(mb * 128 + 64 * wg), "r"(hg * 80), "r"(so) : "memory");
            asm volatile("cp.async.bulk.commit_group;" ::: "memory");
        }
        __syncwarp();
        const float p0 = *(volatile const float*)&rw[g].x, p1 = *(volatile const float*)&rw[g + 8].x;
        float s[3][4] = {};
        const uint32_t pp[2] = {__byte_perm(__float_as_uint(p0), 0, 0x3232), __byte_perm(__float_as_uint(p1), 0, 0x3232)};
#pragma unroll
        for (int j = 0; j < 10; j += 2) {
            const uint32_t d0 = sub2(xr[j][0], pp[0]), d1 = sub2(xr[j][1], pp[1]), d2 = sub2(xr[j + 1][0], pp[0]), d3 = sub2(xr[j + 1][1], pp[1]);
            mma_bf16(s[0], xr[j][0], xr[j][1], xr[j + 1][0], xr[j + 1][1], 0x3f803f80u, 0x3f803f80u);
            mma_bf16(s[1], d0, d1, d2, d3, d0, d2);
            mma_bf16(s[2], d0, d1, d2, d3, d1, d3);
        }
        if (t == (g >> 1)) {
            float2* rp = rsum + ri;
            asm volatile("red.relaxed.gpu.global.add.v2.f32 [%0], {%1, %2};" ::"l"(rp), "f"(fmaf(-80.f, p0, s[0][0])), "f"((g & 1) ? s[1][1] : s[1][0]) : "memory");
            asm volatile("red.relaxed.gpu.global.add.v2.f32 [%0], {%1, %2};" ::"l"(rp + 4), "f"(fmaf(-80.f, p1, s[0][2])), "f"((g & 1) ? s[2][3] : s[2][2]) : "memory");
        }
        asm volatile("cp.async.bulk.wait_group.read 0;" ::: "memory");
        TSTAMP2(6);
        if (tid == 0) DBGC(63);
        if (tid == 128) DBGC(28);
        if (tid == 0) DBGCAL(2);
        GSTAMP(g_tim1, 14);
        SPAN(1 + 4 * layer, 3);
    }
}

static int h_nsm;
static void* h_sym[11];
static TileTab h_tab;
static CUtensorMap h_tmX0, h_tmX1, h_tmR0, h_tmR1, h_tmX1st, h_tmOut, h_tmWq, h_tmWo, h_tmWt;
typedef CUresult (*PFN_encodeTiled)(CUtensorMap*, CUtensorMapDataType, cuuint32_t, void*, const cuuint64_t*, const cuuint64_t*,
                                    const cuuint32_t*, const cuuint32_t*, CUtensorMapInterleave, CUtensorMapSwizzle,
                                    CUtensorMapL2promotion, CUtensorMapFloatOOBfill);
static void make_tmap(CUtensorMap* tm, const void* ptr, uint64_t cols, uint64_t rows, uint32_t bc, uint32_t br, CUtensorMapSwizzle sw, uint64_t pitch = 0, uint64_t hi = 0, uint32_t bh = 2) {
    static PFN_encodeTiled fn = nullptr;
    if (!fn) {
        void* p = nullptr; cudaDriverEntryPointQueryResult qr;
        cudaGetDriverEntryPoint("cuTensorMapEncodeTiled", &p, cudaEnableDefault, &qr);
        fn = (PFN_encodeTiled)p;
    }
    if (br == 0) {
        cuuint64_t dims[5] = {16, 2, rows / 8, 4, cols / 16}; cuuint64_t strides[4] = {cols * 2, cols * 16, cols * 4, 32};
        cuuint32_t box[5] = {16, 2, bc, 4, 5}; cuuint32_t es[5] = {1, 1, 1, 1, 1};
        fn(tm, CU_TENSOR_MAP_DATA_TYPE_BFLOAT16, 5, const_cast<void*>(ptr), dims, strides, box, es, CU_TENSOR_MAP_INTERLEAVE_NONE, sw,
           CU_TENSOR_MAP_L2_PROMOTION_L2_128B, CU_TENSOR_MAP_FLOAT_OOB_FILL_NONE);
        return;
    }
    if (bh == 0) {
        cuuint64_t dims[5] = {64, 64, 2, 16, 10}; cuuint64_t strides[4] = {pitch * 2, hi * 2, cols * 2, rows * 2};
        cuuint32_t box[5] = {64, 64, 2, 1, 1}; cuuint32_t es[5] = {1, 1, 1, 1, 1};
        fn(tm, CU_TENSOR_MAP_DATA_TYPE_BFLOAT16, 5, const_cast<void*>(ptr), dims, strides, box, es, CU_TENSOR_MAP_INTERLEAVE_NONE, sw,
           CU_TENSOR_MAP_L2_PROMOTION_L2_128B, CU_TENSOR_MAP_FLOAT_OOB_FILL_NONE);
        return;
    }
    if (hi) {
        cuuint64_t dims[3] = {cols, rows, hi == 64 ? 32u : hi == 16 ? 120u : 2u}; cuuint64_t strides[2] = {pitch * 2, hi * 2};
        cuuint32_t box[3] = {bc, br, bh}; cuuint32_t es[3] = {1, 1, 1};
        fn(tm, CU_TENSOR_MAP_DATA_TYPE_BFLOAT16, 3, const_cast<void*>(ptr), dims, strides, box, es, CU_TENSOR_MAP_INTERLEAVE_NONE, sw,
           CU_TENSOR_MAP_L2_PROMOTION_L2_128B, CU_TENSOR_MAP_FLOAT_OOB_FILL_NONE);
        return;
    }
    cuuint64_t dims[2] = {cols, rows}; cuuint64_t strides[1] = {(pitch ? pitch : cols) * 2};
    cuuint32_t box[2] = {bc, br}; cuuint32_t es[2] = {1, 1};
    fn(tm, CU_TENSOR_MAP_DATA_TYPE_BFLOAT16, 2, const_cast<void*>(ptr), dims, strides, box, es, CU_TENSOR_MAP_INTERLEAVE_NONE, sw,
       CU_TENSOR_MAP_L2_PROMOTION_L2_128B, CU_TENSOR_MAP_FLOAT_OOB_FILL_NONE);
}
template <typename... Args>
static void launch_pdl(void (*kern)(Args...), int grid, int block, int smem, Args... args) {
    cudaLaunchConfig_t cfg = {};
    cfg.gridDim = dim3(grid); cfg.blockDim = dim3(block); cfg.dynamicSmemBytes = smem; cfg.stream = cudaStreamPerThread;
    cudaLaunchAttribute at[1];
    at[0].id = cudaLaunchAttributeProgrammaticStreamSerialization; at[0].val.programmaticStreamSerializationAllowed = 1;
    cfg.attrs = at; cfg.numAttrs = 1;
    cudaLaunchKernelEx(&cfg, kern, args...);
}
static void launch_stage(int k, void* const* d_in, void* d_out) {
    const KgIn kg = {(const bf16*)d_in[4], (const bf16*)d_in[5], (const bf16*)d_in[6], (const bf16*)d_in[7], (const bf16*)d_in[8], (const bf16*)d_in[9], (const bf16*)d_in[0], (const bf16*)d_in[1], (const bf16*)d_in[2],
                      (uint4*)h_sym[0], (uint4*)h_sym[1], (uint4*)h_sym[2], (uint4*)h_sym[3], (uint4*)h_sym[4], (float*)h_sym[5]};
    switch (k) {
        case 0: kgen_kernel<<<128, 512, KG_SMEM, cudaStreamPerThread>>>(kg, h_tmWq, h_tmWo, h_tmWt); break;
        case 1: launch_pdl(a1_kernel, h_nsm, A1_THREADS, A1_SMEM, 0, (const bf16*)d_in[0], (const unsigned char*)h_sym[1], (const unsigned char*)h_sym[2], (float2*)h_sym[4], (uint4*)h_sym[6], h_tmX0, h_tmR0, h_tmX1st, h_tab); break;
        case 3: launch_pdl(conv_kernel, DM / CV_CPB, CV_THREADS, CV_SMEM, 0, (const uint4*)h_sym[7], (const float4*)h_sym[4], (const bf16*)h_sym[8], (bf16*)h_sym[9], (const uint4*)h_sym[0], (bf16*)h_sym[10], h_tmOut); break;
        case 5: launch_pdl(a1_kernel, h_nsm, A1_THREADS, A1_SMEM, 1, (const bf16*)d_in[0], (const unsigned char*)h_sym[1], (const unsigned char*)h_sym[2], (float2*)h_sym[4], (uint4*)h_sym[6], h_tmX1, h_tmR1, h_tmX1st, h_tab); break;
        case 7: launch_pdl(conv_kernel, DM / CV_CPB, CV_THREADS, CV_SMEM, 1, (const uint4*)h_sym[7] + SEQ / 8, (const float4*)h_sym[4] + SEQ / 2, (const bf16*)h_sym[8], (bf16*)h_sym[10], (const uint4*)h_sym[0], (bf16*)h_sym[10], h_tmOut); break;
        default: break;
    }
}
static int n_stage_kernels() { return 9; }
static const char* stage_name(int k) { const char* n[] = {"kgen", "a1", "a2", "conv", "tr", "a1", "a2", "conv", "tr"}; return n[k]; }

extern "C" void kernel_launch(void* const* d_in, const int* in_sizes, int n_in, void* d_out, int out_size) {
    (void)in_sizes; (void)n_in; (void)out_size;
    static const void *p_in = nullptr, *p_w1 = nullptr, *p_w2 = nullptr, *p_out = nullptr;
    if (p_in != d_in[0] || p_w1 != d_in[1] || p_w2 != d_in[2] || p_out != d_out) {
        cudaFuncSetAttribute(conv_kernel, cudaFuncAttributeMaxDynamicSharedMemorySize, CV_SMEM);
        cudaFuncSetAttribute(kgen_kernel, cudaFuncAttributeMaxDynamicSharedMemorySize, KG_SMEM);
        cudaFuncSetAttribute(a1_kernel, cudaFuncAttributeMaxDynamicSharedMemorySize, A1_SMEM);
        int dev; cudaGetDevice(&dev); cudaDeviceGetAttribute(&h_nsm, cudaDevAttrMultiProcessorCount, dev);
        if (h_nsm != 132) h_nsm = 128;
        h_tab.ns = h_nsm == 132 ? 132 : ~0u;
        for (int i = 0; i < 264; i++) {
            const int h = (i - 64) >> 1;
            const int t = i >= 132 ? i - 132 : i < 64 ? ((i >> 1) & 7) * 16 + (i >> 4) * 2 + (i & 1) : i < 120 ? (1 + h % 7) * 16 + 8 + (h / 7) * 2 + (i & 1) : i < 124 ? 128 : i - 116;
            const int hg = (4 * (t >> 6) + (t & 3)) & 7;
            h_tab.e[i] = {(unsigned char)((t >> 2) & 15), (unsigned char)hg, (unsigned char)(5 * (hg >> 2)), (unsigned char)t, (uint32_t)(hg * 10 * WQ_STAGE)};
        }
        cudaGetSymbolAddress(&h_sym[0], g_tap); cudaGetSymbolAddress(&h_sym[1], g_wq); cudaGetSymbolAddress(&h_sym[2], g_wo);
        cudaGetSymbolAddress(&h_sym[3], g_halo); cudaGetSymbolAddress(&h_sym[4], g_sum); cudaGetSymbolAddress(&h_sym[5], g_csp); cudaGetSymbolAddress(&h_sym[6], g_of);
        cudaGetSymbolAddress(&h_sym[7], g_piv); cudaGetSymbolAddress(&h_sym[8], g_x1T); cudaGetSymbolAddress(&h_sym[9], g_xcT); cudaGetSymbolAddress(&h_sym[10], g_yT);
        void *px1, *px2;
        cudaGetSymbolAddress(&px1, g_x1T); cudaGetSymbolAddress(&px2, g_xcT);
        make_tmap(&h_tmX0, d_in[0], 128 * 640, 64, 64, 64, CU_TENSOR_MAP_SWIZZLE_128B, 1280, 640, 0);
        make_tmap(&h_tmX1, px2, 128, 64 * XCP, 64, 64, CU_TENSOR_MAP_SWIZZLE_128B, XCP, 64, 0);
        make_tmap(&h_tmR0, d_in[0], 640, 1024, 80, 64, CU_TENSOR_MAP_SWIZZLE_NONE, 1280, 640, 1);
        make_tmap(&h_tmR1, px2, 64, 640, 64, 80, CU_TENSOR_MAP_SWIZZLE_128B, XCP, 64, 1);
        make_tmap(&h_tmX1st, px1, 2048, 640, 64, 80, CU_TENSOR_MAP_SWIZZLE_128B, XCP);
        make_tmap(&h_tmWq, d_in[1], 16, 640, 16, 32, CU_TENSOR_MAP_SWIZZLE_32B, 1920, 16, 5);
        make_tmap(&h_tmWo, d_in[2], 640, 640, 4, 0, CU_TENSOR_MAP_SWIZZLE_32B);
        make_tmap(&h_tmWt, d_in[2], 640, 640, 2, 0, CU_TENSOR_MAP_SWIZZLE_32B);
        make_tmap(&h_tmOut, d_out, 640, 2048, 80, 8, CU_TENSOR_MAP_SWIZZLE_NONE);
        p_in = d_in[0]; p_w1 = d_in[1]; p_w2 = d_in[2]; p_out = d_out;
    }
    for (int k = 0; k < n_stage_kernels(); k++) launch_stage(k, d_in, d_out);
}
```

```cpp
#include <cuda_runtime.h>
#include <cuda_bf16.h>
#include <stdint.h>
#include <cuda.h>

typedef __nv_bfloat16 bf16;

constexpr int SEQ = 2048;
constexpr int DM = 640;
constexpr int NMODE = 192;

__device__ __forceinline__ float bf2f(bf16 v) { return __bfloat162float(v); }
__device__ __forceinline__ float rbf(float v) {
    uint32_t r;
    asm("cvt.rn.bf16x2.f32 %0, %1, %2;" : "=r"(r) : "f"(v), "f"(0.f));
    return __uint_as_float(r);
}
__device__ __forceinline__ uint32_t pack2(float lo, float hi) {
    __nv_bfloat162 t = __floats2bfloat162_rn(lo, hi);
    return *reinterpret_cast<uint32_t*>(&t);
}
__device__ __forceinline__ void pdl_sync() {
    asm volatile("griddepcontrol.wait;" ::: "memory");
    asm volatile("griddepcontrol.launch_dependents;" ::: "memory");
}
__device__ __forceinline__ float sqrt_apx(float v) { float r; asm("sqrt.approx.ftz.f32 %0, %1;" : "=f"(r) : "f"(v)); return r; }
__device__ __forceinline__ float rcp_apx(float v) { float r; asm("rcp.approx.ftz.f32 %0, %1;" : "=f"(r) : "f"(v)); return r; }
__device__ __forceinline__ uint32_t smem_u32(const void* p) { return (uint32_t)__cvta_generic_to_shared(p); }

constexpr int TAPB = 2 * 152 * 8;
__device__ __align__(128) uint4 g_tap[DM * 128];
#define XPAD 64
constexpr int XCP = SEQ + XPAD;
__device__ __align__(128) bf16 g_x1T[DM * XCP];
__device__ __align__(128) bf16 g_xcT[DM * XCP];
__device__ __align__(128) uint4 g_of[128 * 1280];
constexpr int WQ_STAGE = 240 * 128, WOB = 80 * 160;
__device__ __align__(128) uint4 g_wq[8 * 10 * WQ_STAGE / 16];
__device__ __align__(128) uint4 g_wo[64 * WOB / 16];
__device__ __align__(16) float g_csp[10 * 1920];
#define FSTR 32
__device__ __align__(128) float2 g_sum[2 * SEQ + 256 * FSTR];
__device__ __align__(16) bf16 g_piv[2 * SEQ];
__device__ __align__(128) bf16 g_yT[DM * XCP];
__device__ uint32_t g_epoch;
__device__ __align__(16) unsigned long long g_rstat[SEQ];
__device__ __align__(128) uint4 g_halo[640 * 148];
__device__ __forceinline__ unsigned long long tagw(uint32_t payload, uint32_t tag) { return ((unsigned long long)tag << 32) | payload; }
__device__ __forceinline__ ulonglong2 ld_tag2(const ulonglong2* p) {
    ulonglong2 v;
    asm volatile("ld.relaxed.gpu.global.v2.u64 {%0, %1}, [%2];" : "=l"(v.x), "=l"(v.y) : "l"(p) : "memory");
    return v;
}
__device__ __forceinline__ bool tag_ok(ulonglong2 v, uint32_t tag) { return (uint32_t)(v.x >> 32) == tag && (uint32_t)(v.y >> 32) == tag; }
__device__ __forceinline__ uint32_t ld_epoch() { uint32_t v; asm volatile("ld.relaxed.gpu.global.u32 %0, [%1];" : "=r"(v) : "l"(&g_epoch) : "memory"); return v + 1; }
constexpr int SPIN_MAX = 1 << 20;
__device__ uint32_t g_started[4];
__device__ __forceinline__ void sm_started(int slot) { asm volatile("red.relaxed.gpu.global.add.u32 [%0], 1;" ::"l"(g_started + slot) : "memory"); }
__device__ __noinline__ void sm_idle(int slot) {
    if (threadIdx.x) return;
    sm_started(slot);
    const uint32_t want = ld_epoch() * gridDim.x;
    pdl_sync();
#pragma unroll 1
    for (int it = 0; it < SPIN_MAX; it++) {
        uint32_t v;
        asm volatile("ld.relaxed.gpu.global.u32 %0, [%1];" : "=r"(v) : "l"(g_started + slot) : "memory");
        if ((int)(v - want) >= 0) break;
        __nanosleep(100);
    }
}
struct TileTab { uint32_t ns, pad; struct { unsigned char mb, hg, kb0, tile; uint32_t woff; } __align__(8) e[264]; };
__device__ __forceinline__ bool elect() {
    uint32_t p;
    asm volatile("{\n.reg .pred p;\nelect.sync _|p, 0xffffffff;\nselp.b32 %0, 1, 0, p;\n}" : "=r"(p));
    return p;
}
#define DBG_SYMS
#define TSTAMP(i)
#define TSTAMP1(i)
#define TSTAMP1T(i, t)
#define TSTAMP1X(i, t)
#define SPAN(k, i)
#define GSTAMP(arr, i)
#define TSTAMP2(i)
#define TSTAMP3(i)
#define TSTAMP4(i)
#define TSTAMPK(i, t)
#define TSTAMPC(i)
#define DBGC(i)
#define DBGV(i, v)
#define DBGCAL(i)

#define CST(i)
#define CST_END
#define CST_EXTRA 0
__device__ __forceinline__ void mma_bf16(float* d, uint32_t a0, uint32_t a1, uint32_t a2, uint32_t a3, uint32_t b0, uint32_t b1) {
    asm volatile("mma.sync.aligned.m16n8k16.row.col.f32.bf16.bf16.f32 {%0,%1,%2,%3}, {%4,%5,%6,%7}, {%8,%9}, {%0,%1,%2,%3};"
                 : "+f"(d[0]), "+f"(d[1]), "+f"(d[2]), "+f"(d[3]) : "r"(a0), "r"(a1), "r"(a2), "r"(a3), "r"(b0), "r"(b1));
}
__device__ __forceinline__ void mma_bf16_k8(float* d, uint32_t a0, uint32_t a1, uint32_t b0) {
    asm volatile("mma.sync.aligned.m16n8k8.row.col.f32.bf16.bf16.f32 {%0,%1,%2,%3}, {%4,%5}, {%6}, {%0,%1,%2,%3};"
                 : "+f"(d[0]), "+f"(d[1]), "+f"(d[2]), "+f"(d[3]) : "r"(a0), "r"(a1), "r"(b0));
}
__device__ __forceinline__ void ldsm_x4(uint32_t* r, uint32_t addr) {
    asm volatile("ldmatrix.sync.aligned.m8n8.x4.shared.b16 {%0,%1,%2,%3}, [%4];"
                 : "=r"(r[0]), "=r"(r[1]), "=r"(r[2]), "=r"(r[3]) : "r"(addr));
}

__device__ __forceinline__ void ldsm_x4_t(uint32_t* r, uint32_t addr) {
    asm volatile("ldmatrix.sync.aligned.m8n8.x4.trans.shared.b16 {%0,%1,%2,%3}, [%4];"
                 : "=r"(r[0]), "=r"(r[1]), "=r"(r[2]), "=r"(r[3]) : "r"(addr));
}
__device__ __forceinline__ void mbar_init(uint32_t bar, int count) { asm volatile("mbarrier.init.shared::cta.b64 [%0], %1;" ::"r"(bar), "r"(count)); }
__device__ __forceinline__ void mbar_arrive(uint32_t bar) { asm volatile("mbarrier.arrive.shared::cta.b64 _, [%0];" ::"r"(bar) : "memory"); }
__device__ __forceinline__ void mbar_wait(uint32_t bar, uint32_t parity) {
    asm volatile("{\n.reg .pred p;\nWAIT_LOOP:\n"
                 "mbarrier.try_wait.parity.shared::cta.b64 p, [%0], %1;\n"
                 "@p bra.uni WAIT_DONE;\nbra.uni WAIT_LOOP;\nWAIT_DONE:\n}" ::"r"(bar), "r"(parity) : "memory");
}

__device__ __forceinline__ void mbar_expect_tx(uint32_t bar, uint32_t bytes) {
    asm volatile("mbarrier.arrive.expect_tx.shared::cta.b64 _, [%0], %1;" ::"r"(bar), "r"(bytes) : "memory");
}
__device__ __forceinline__ void tma_load_2d(uint32_t dst, const void* tmap, int c0, int c1, uint32_t bar) {
    asm volatile("cp.async.bulk.tensor.2d.shared::cluster.global.mbarrier::complete_tx::bytes [%0], [%1, {%3, %4}], [%2];"
                 ::"r"(dst), "l"(tmap), "r"(bar), "r"(c0), "r"(c1) : "memory");
}
__device__ __forceinline__ void tma_load_3d(uint32_t dst, const void* tmap, int c0, int c1, int c2, uint32_t bar) {
    asm volatile("cp.async.bulk.tensor.3d.shared::cluster.global.mbarrier::complete_tx::bytes [%0], [%1, {%3, %4, %5}], [%2];"
                 ::"r"(dst), "l"(tmap), "r"(bar), "r"(c0), "r"(c1), "r"(c2) : "memory");
}
__device__ __forceinline__ void fence_async_smem() { asm volatile("fence.proxy.async.shared::cta;" ::: "memory"); }
__device__ __forceinline__ void bulk_load(uint32_t dst, const void* src, uint32_t bytes, uint32_t bar) {
    asm volatile("cp.async.bulk.shared::cluster.global.mbarrier::complete_tx::bytes [%0], [%1], %2, [%3];"
                 ::"r"(dst), "l"(src), "r"(bytes), "r"(bar) : "memory");
}
__device__ __forceinline__ void stsm_x4(uint32_t addr, uint32_t r0, uint32_t r1, uint32_t r2, uint32_t r3) {
    asm volatile("stmatrix.sync.aligned.m8n8.x4.shared.b16 [%0], {%1,%2,%3,%4};" ::"r"(addr), "r"(r0), "r"(r1), "r"(r2), "r"(r3) : "memory");
}
__device__ __forceinline__ void stsm_x4_t(uint32_t addr, uint32_t r0, uint32_t r1, uint32_t r2, uint32_t r3) {
    asm volatile("stmatrix.sync.aligned.m8n8.x4.trans.shared.b16 [%0], {%1,%2,%3,%4};" ::"r"(addr), "r"(r0), "r"(r1), "r"(r2), "r"(r3) : "memory");
}
__device__ __forceinline__ void prefetch_tmap(const void* tmap) { asm volatile("prefetch.tensormap [%0];" ::"l"(tmap) : "memory"); }

__device__ __forceinline__ float2 cexp_at(float wr2, float wi, float p) {
    float er;
    asm("ex2.approx.ftz.f32 %0, %1;" : "=f"(er) : "f"(wr2 * p));
    float th = wi * p;
    const float k = rintf(th * 0.15915494309189535f);
    th = fmaf(k, -6.2831854820251465f, th);
    th = fmaf(k, 1.7484555314695172e-7f, th);
    return make_float2(er * __cosf(th), er * __sinf(th));
}
__device__ __forceinline__ float2 cmul(float2 a, float2 b) {
    return make_float2(fmaf(a.x, b.x, -a.y * b.y), fmaf(a.x, b.y, a.y * b.x));
}
__device__ __forceinline__ float2 csqr(float2 a) { return make_float2(fmaf(a.x, a.x, -a.y * a.y), (a.x + a.x) * a.y); }
__device__ __forceinline__ uint32_t packh(float2 v) {
    uint32_t r;
    asm("cvt.rn.f16x2.f32 %0, %1, %2;" : "=r"(r) : "f"(v.y), "f"(v.x));
    return r;
}
__device__ __forceinline__ void mma_f16(float* d, uint32_t a0, uint32_t a1, uint32_t a2, uint32_t a3, uint32_t b0, uint32_t b1) {
    asm volatile("mma.sync.aligned.m16n8k16.row.col.f32.f16.f16.f32 {%0,%1,%2,%3}, {%4,%5,%6,%7}, {%8,%9}, {%0,%1,%2,%3};"
                 : "+f"(d[0]), "+f"(d[1]), "+f"(d[2]), "+f"(d[3]) : "r"(a0), "r"(a1), "r"(a2), "r"(a3), "r"(b0), "r"(b1));
}

struct KgIn { const bf16 *logA, *Aim, *Cre, *Cim, *logdt, *dsk, *x, *wqkv, *wo; uint4 *tap, *wq, *wop, *halo, *sum; float* csp; };
constexpr int KG_THREADS = NMODE / 2;

constexpr int KG_BUF = 15 * 12288, KG_BAR = KG_BUF + 6 * 5120, KG_SMEM = KG_BAR + 64;
__global__ void __launch_bounds__(512, 1) kgen_kernel(const KgIn in, const __grid_constant__ CUtensorMap tmWq, const __grid_constant__ CUtensorMap tmWo,
                                                        const __grid_constant__ CUtensorMap tmWt) {
    extern __shared__ __align__(1024) uint4 tabs[];
#define KG_ROT 0
    const int lane = threadIdx.x & 31, w16 = (__shfl_sync(~0u, threadIdx.x >> 5, 0) + KG_ROT) & 15, grp = w16 / 3, warp = w16 - 3 * grp;
    const int d = blockIdx.x * 5 + grp, tid = warp * 32 + lane;
    uint4* tab = tabs + grp * (3 * 768);
    SPAN(0, 0); SPAN(0, 1);
    TSTAMPK(0, 0);
    asm volatile("griddepcontrol.launch_dependents;" ::: "memory");
    if (w16 == 15) {
        const uint32_t b0 = smem_u32(tab), wbar = b0 + 6 * 5120;
        const int blk = blockIdx.x, nq = blk < 112 ? 4 : 2, nj = nq + (blk < 64 ? 1 : 2);
        auto fetch = [&](int i) {
            const uint32_t dst = b0 + i * 5120, bar = wbar + 8 * i;
            if (i < nq) {
                const int p = blk + 64 * (i & 2), kb = p / 24;
                mbar_expect_tx(bar, 5120);
                tma_load_3d(dst, &tmWq, 0, kb * 64 + (i & 1) * 32, (p - 24 * kb) * 5, bar);
            } else if (i < nj) {
                const int o = i == nq ? blk : 255 - blk;
                mbar_expect_tx(bar, o < 128 ? 5120 : 2560);
                asm volatile("cp.async.bulk.tensor.5d.shared::cluster.global.mbarrier::complete_tx::bytes [%0], [%1, {%3, %3, %4, %3, %5}], [%2];"
                             ::"r"(dst), "l"(o < 128 ? &tmWo : &tmWt), "r"(bar), "r"(0), "r"((o & 7) * 10 + (o >> 6) * 4), "r"(((o >> 3) & 7) * 5) : "memory");
            }
        };
        const bool one = elect();
        if (one) {
#pragma unroll
            for (int i = 0; i < 6; i++) mbar_init(wbar + 8 * i, 1);
            asm volatile("fence.mbarrier_init.release.cluster;" ::: "memory");
#pragma unroll
            for (int i = 0; i < 6; i++) fetch(i);
        }
        __syncwarp();
#pragma unroll
        for (int i = 1; i <= 5; i++) asm volatile("bar.arrive %0, 128;" ::"r"(i) : "memory");
        if (one) {
#pragma unroll 1
            for (int i = 0; i < nj; i++) {
                const int p = blk + 64 * (i & 2), kb = p / 24, hg = p & 7, sec = (p - 24 * kb) >> 3, o = i == nq ? blk : 255 - blk, cg = (o >> 3) & 7, hb = o & 7;
                const unsigned char* dst = i < nq ? reinterpret_cast<unsigned char*>(in.wq) + (hg * 10 + (hg < 4 ? kb : kb < 5 ? kb + 5 : kb - 5)) * WQ_STAGE + ((i & 1) * 3 + sec) * 5120
                                                  : reinterpret_cast<unsigned char*>(in.wop) + (cg * 8 + (hb == cg ? 0 : hb + (hb < cg))) * WOB + (o >> 6) * 5120;
                mbar_wait(wbar + 8 * i, 0);
                if (i == 0) TSTAMPK(2, (15 - KG_ROT) * 32);
                if (i == 3) TSTAMPK(5, (15 - KG_ROT) * 32);
                asm volatile("cp.async.bulk.global.shared::cta.bulk_group [%0], [%1], %2;" ::"l"(dst), "r"(b0 + i * 5120), "r"(i < nq || o < 128 ? 5120 : 2560) : "memory");
            }
            asm volatile("cp.async.bulk.commit_group;" ::: "memory");
            asm volatile("cp.async.bulk.wait_group.read 0;" ::: "memory");
        }
        TSTAMPK(11, (15 - KG_ROT) * 32);
        return;
    }
    const bf16 pdt = in.logdt[d], pdsk = in.dsk[d];
    const uint32_t pla = reinterpret_cast<const uint32_t*>(in.logA)[d * KG_THREADS + tid], pai = reinterpret_cast<const uint32_t*>(in.Aim)[d * KG_THREADS + tid];
    const uint32_t pcr = reinterpret_cast<const uint32_t*>(in.Cre)[d * KG_THREADS + tid], pci = reinterpret_cast<const uint32_t*>(in.Cim)[d * KG_THREADS + tid];
    const bf16* pfq = tid < 30 ? in.wqkv + (size_t)(d * 30 + tid) * 64 : tid < 40 ? in.wo + (size_t)(d * 10 + tid - 30) * 64 : in.x + (size_t)(d * 32 + tid - 40) * 64;
#define KG_PF 0
    if (tid < (KG_PF == 3 ? 0 : KG_PF ? 40 : 72)) asm volatile("prefetch.global.L2 [%0];" ::"l"(pfq));
    asm volatile("st.global.v4.u32 [%0], {%1,%1,%1,%1};" ::"l"(in.halo + d * 148 + tid), "r"(~0u));
    if (tid < 52) asm volatile("st.global.v4.u32 [%0], {%1,%1,%1,%1};" ::"l"(in.halo + d * 148 + 96 + tid), "r"(~0u));
    else if (w16 == 2) {
        if (lane < 16) in.sum[blockIdx.x * 16 + lane] = make_uint4(0, 0, 0, 0);
        else if (lane < 20) reinterpret_cast<uint32_t*>(in.sum + 2048)[(blockIdx.x * 4 + lane - 16) * FSTR] = 0;
    }
    const uint32_t tw = smem_u32(tab) + warp * 12288;
    const int g = lane >> 2, t = lane & 3;
    const uint32_t sta = tw + lane * 128 + ((2 * (lane & 3) + ((lane >> 2) & 1)) << 4);
    const uint32_t lda = tw + t * 128 + ((g ^ (2 * t)) << 4);
    const uint32_t stb = tw + lane * 8, ldb = tw + g * 512 + (g & 3) * 32 + t * 8;
    auto sts4 = [&](int e, int off, uint32_t a, uint32_t b, uint32_t c, uint32_t dd) {
        asm volatile("st.shared.v4.u32 [%0], {%1,%2,%3,%4};" ::"r"((sta ^ (e << 4)) + off), "r"(a), "r"(b), "r"(c), "r"(dd) : "memory");
    };
    auto lds4 = [&](int sp, int off, uint32_t* r) {
        asm volatile("ld.shared.v4.u32 {%0,%1,%2,%3}, [%4];" : "=r"(r[0]), "=r"(r[1]), "=r"(r[2]), "=r"(r[3]) : "r"((lda ^ ((sp & 1) << 4)) + sp * 512 + off) : "memory");
    };
    const float dt = rbf(expf(bf2f(pdt)));
    float2 C[2], y1[2], z8[2], y128[2];
    float cmax = 0.f;
#pragma unroll
    for (int m = 0; m < 2; m++) {
        const float wr2 = -rbf(expf(__uint_as_float(m ? pla & 0xffff0000u : pla << 16))) * dt * 1.4426950408889634f;
        const float wi = __uint_as_float(m ? pai & 0xffff0000u : pai << 16) * dt;
        C[m] = make_float2(__uint_as_float(m ? pcr & 0xffff0000u : pcr << 16) * dt, -__uint_as_float(m ? pci & 0xffff0000u : pci << 16) * dt);
        cmax = fmaxf(cmax, fmaxf(fabsf(C[m].x), fabsf(C[m].y)));
        y1[m] = cexp_at(wr2, -wi, 1.f); z8[m] = cexp_at(wr2, wi, 8.f); y128[m] = cexp_at(wr2, -wi, 128.f);
    }
    const int ex = min(max((int)(__reduce_max_sync(~0u, __float_as_uint(cmax)) >> 23), 20), 240);
    const float scale = __uint_as_float((uint32_t)(127 + 10 + 127 - ex) << 23), unscale = 2.0f * __uint_as_float((uint32_t)(ex - 10) << 23);
    TSTAMPK(4, 64);
    if (KG_PF >= 2 && tid >= 40 && tid < 72) asm volatile("prefetch.global.L2 [%0];" ::"l"(pfq));
    float k2048 = 0.f;
    float acc[5][4];
#pragma unroll
    for (int j = 0; j < 5; j++)
#pragma unroll
        for (int k = 0; k < 4; k++) acc[j][k] = 0.f;
    uint32_t af[8][4];
    {
        float2 h0[2], h1[2], g0[2], g1[2], g2[2], g2b[2], g3[2], g4[2], y2[2], y4[2];
#pragma unroll
        for (int m = 0; m < 2; m++) {
            h0[m] = make_float2(1.f, 0.f); h1[m] = csqr(csqr(csqr(z8[m])));
            g0[m] = make_float2(C[m].x * scale, C[m].y * scale);
            g1[m] = cmul(g0[m], y128[m]);
            const float2 y256 = csqr(y128[m]), y512 = csqr(y256);
            g2b[m] = g2[m] = cmul(g0[m], y256); g3[m] = cmul(g0[m], y512); g4[m] = cmul(g3[m], y512);
            y2[m] = csqr(y1[m]); y4[m] = csqr(y2[m]);
            const float2 y1024 = csqr(y512);
            k2048 += fmaf(g4[m].x, y1024.x, -g4[m].y * y1024.y);
        }
#pragma unroll
        for (int e = 0; e < 8; e++) {
            sts4(e, 0, packh(h0[0]), packh(h1[0]), packh(h0[1]), packh(h1[1]));
            sts4(e, 4096, packh(g0[0]), packh(g0[1]), packh(g1[0]), packh(g1[1]));
#pragma unroll
            for (int m = 0; m < 2; m++)
                if (e < 7) { h0[m] = e ? cmul(h0[m], z8[m]) : z8[m]; h1[m] = cmul(h1[m], z8[m]); g0[m] = cmul(g0[m], y1[m]); g1[m] = cmul(g1[m], y1[m]); }
            if (e < 5) k2048 += __shfl_xor_sync(~0u, k2048, 1 << e);
        }
        if (KG_PF == 1 && tid >= 40 && tid < 72) asm volatile("prefetch.global.L2 [%0];" ::"l"(pfq));
        __syncwarp();
#pragma unroll
        for (int e = 0; e < 8; e++) {
            uint32_t b[4];
            lds4(e, 0, af[e]); lds4(e, 4096, b);
            sts4(e, 8192, packh(g2[0]), packh(g2[1]), packh((e & 1) ? cmul(g3[0], y4[0]) : g3[0]), packh((e & 1) ? cmul(g3[1], y4[1]) : g3[1]));
            asm volatile("st.shared.v2.u32 [%0], {%1,%2};" ::"r"((stb ^ ((e & 3) << 5)) + e * 512), "r"(packh(g4[0])), "r"(packh(g4[1])) : "memory");
#pragma unroll
            for (int m = 0; m < 2; m++)
                if (e < 7) {
                    g2[m] = e == 3 ? cmul(g2b[m], y128[m]) : cmul(g2[m], y2[m]);
                    if (e & 1) g3[m] = cmul(g3[m], y128[m]);
                    g4[m] = cmul(g4[m], y128[m]);
                }
            mma_f16(acc[0], af[e][0], af[e][1], af[e][2], af[e][3], b[0], b[1]);
            mma_f16(acc[1], af[e][0], af[e][1], af[e][2], af[e][3], b[2], b[3]);
        }
    }
    TSTAMPK(6, 64);
    __syncwarp();
#pragma unroll
    for (int sp = 0; sp < 8; sp++) {
        uint32_t c[4], e0, e1;
        lds4(sp, 8192, c);
        asm volatile("ld.shared.v2.u32 {%0,%1}, [%2];" : "=r"(e0), "=r"(e1) : "r"(ldb ^ (sp << 5)) : "memory");
        mma_f16(acc[2], af[sp][0], af[sp][1], af[sp][2], af[sp][3], c[0], c[1]);
        mma_f16(acc[3], af[sp][0], af[sp][1], af[sp][2], af[sp][3], c[2], c[3]);
        mma_f16(acc[4], af[sp][0], af[sp][1], af[sp][2], af[sp][3], e0, e1);
    }
    {
        float* Pp = reinterpret_cast<float*>(tab + warp * 768);
        auto sw = [](int i) { return i ^ ((i >> 2) & 24); };
#pragma unroll
        for (int h = 0; h < 2; h++) {
            const int b = g + 8 * h;
            *reinterpret_cast<float2*>(Pp + sw(8 * b + 2 * t)) = make_float2(acc[0][2 * h] * unscale, acc[0][2 * h + 1] * unscale);
            *reinterpret_cast<float2*>(Pp + 128 + sw(8 * b + 2 * t)) = make_float2(acc[1][2 * h] * unscale, acc[1][2 * h + 1] * unscale);
            *reinterpret_cast<float2*>(Pp + 256 + sw(4 * b + 2 * (t & 1) + 64 * (t >> 1))) = make_float2(acc[2][2 * h] * unscale, acc[2][2 * h + 1] * unscale);
            *reinterpret_cast<float2*>(Pp + 384 + sw(2 * b + 32 * t)) = make_float2(acc[3][2 * h] * unscale, acc[3][2 * h + 1] * unscale);
            Pp[512 + sw(b + 32 * t)] = acc[4][2 * h] * unscale;
            Pp[512 + sw(b + 32 * t + 16)] = acc[4][2 * h + 1] * unscale;
        }
        if (lane == 0) Pp[640] = k2048 * unscale;
    }
    TSTAMPK(7, 64);
    asm volatile("bar.sync %0, 128;" ::"r"(grp + 1) : "memory");
    TSTAMPK(9, 64);
    const float* Kp = reinterpret_cast<const float*>(tab);
    auto ksum = [&](int i) -> float { return (Kp[i] + Kp[3072 + i]) + Kp[6144 + i]; };
    auto ksum4 = [&](int q) -> float4 {
        q ^= (q >> 2) & 6;
        const float4 a = reinterpret_cast<const float4*>(Kp)[q], b = reinterpret_cast<const float4*>(Kp)[768 + q], c = reinterpret_cast<const float4*>(Kp)[1536 + q];
        return make_float4((a.x + b.x) + c.x, (a.y + b.y) + c.y, (a.z + b.z) + c.z, (a.w + b.w) + c.w);
    };
    {
        uint2* E4 = reinterpret_cast<uint2*>(in.tap + d * 128);
        float4 v = ksum4(tid), u = ksum4(96 + min(tid, 64));
        const float cor = rbf(ksum(tid == 95 ? 384 : 512));
        if (tid == 0) v.x += bf2f(pdsk);
        if (tid == 95) v.w -= cor;
        if (tid == 31) u.w -= cor;
        const uint32_t lo = pack2(v.x, v.y), hi = pack2(v.z, v.w);
        if (tid < 64) {
            E4[6 + tid] = make_uint2(lo, hi);
            E4[(tid < 32 ? 159 : 209 - 32) + tid] = make_uint2(pack2(u.x, u.y), pack2(u.z, u.w));
        } else {
            const uint32_t nx = __shfl_down_sync(~0u, lo, 1);
            in.tap[d * 128 + 35 + tid - 64] = make_uint4(__byte_perm(lo, 0, 0x1010), __byte_perm(lo, hi, 0x5432), __byte_perm(hi, 0, 0x1010), __byte_perm(hi, tid == 95 ? 0u : nx, 0x5432));
            if (tid == 64) E4[241] = make_uint2(pack2(u.x, 0.f), 0u);
        }
    }
    TSTAMPK(10, 64);
    if (warp < (blockIdx.x < 112 ? 2 : 1)) {
        const uint32_t sb = smem_u32(tabs);
        mbar_wait(sb + KG_BAR + 16 * warp, 0); mbar_wait(sb + KG_BAR + 16 * warp + 8, 0);
        uint32_t w[4][4];
        float cs[4] = {0.f, 0.f, 0.f, 0.f};
#pragma unroll
        for (int a = 0; a < 4; a++)
            ldsm_x4_t(w[a], sb + KG_BUF + warp * 10240 + grp * 1024 + ((lane >> 4) * 8 + (lane & 7)) * 32 + ((((lane >> 3) ^ (lane >> 2)) & 1) << 4) + (a >> 1) * 5120 + (a & 1) * 512);
#pragma unroll
        for (int a = 0; a < 4; a++) mma_bf16(cs, w[a][0], w[a][1], w[a][2], w[a][3], 0x3f803f80u, 0x3f803f80u);
        if (t < 2) in.csp[(blockIdx.x + 128 * warp) * 80 + grp * 16 + g + 8 * t] = t ? cs[2] : cs[0];
    }
    SPAN(0, 3);
}

#define CV_SLEEP 100
#define CV_D2 3
#define CV_PDH 12
#define CV_PDF 4
#define CV_HAND 7
constexpr int CV_CPB = 5;
constexpr int CV_THREADS = 512;
constexpr int UPADF = 128;
constexpr int ULEN = UPADF + SEQ;
constexpr int XLEN = SEQ + 16;
constexpr int BX_5 = 0, BX_3 = 3264, BX_9 = 6528, BX_7 = 8960, BX_LEN = 11392;
constexpr int CV_SM_U = 0;
constexpr int CV_SM_T = CV_CPB * ULEN * 2;
constexpr int CV_SM_B = CV_SM_T + CV_CPB * TAPB;
constexpr int CV_SM_X = CV_SM_B + CV_CPB * BX_LEN;
constexpr int CV_SM_Y = (CV_SM_X + CV_CPB * XLEN * 2 + 127) & ~127;
constexpr int CV_SM_CNT = CV_SM_Y + CV_CPB * 8192;
constexpr int CV_SM_O = CV_SM_CNT + 128;
constexpr int CV_SMEM = CV_SM_O + 20480 + CST_EXTRA;
static_assert(ULEN % 128 == 0 && CV_SM_B % 128 == 0 && CV_SM_CNT % 128 == 0, "layout");

__device__ __forceinline__ uint32_t sub2(uint32_t x, uint32_t m) {
    const __nv_bfloat162 d = __hsub2(*reinterpret_cast<const __nv_bfloat162*>(&x), *reinterpret_cast<const __nv_bfloat162*>(&m));
    return *reinterpret_cast<const uint32_t*>(&d);
}
__device__ __forceinline__ uint32_t add2(uint32_t x, uint32_t y) {
    const __nv_bfloat162 d = __hadd2_rn(*reinterpret_cast<const __nv_bfloat162*>(&x), *reinterpret_cast<const __nv_bfloat162*>(&y));
    return *reinterpret_cast<const uint32_t*>(&d);
}
__device__ __forceinline__ void wgmma_fence() { asm volatile("wgmma.fence.sync.aligned;" ::: "memory"); }
__device__ __forceinline__ void wgmma_commit() { asm volatile("wgmma.commit_group.sync.aligned;" ::: "memory"); }
template <int N> __device__ __forceinline__ void wgmma_wait() { asm volatile("wgmma.wait_group.sync.aligned %0;" ::"n"(N) : "memory"); }
__device__ __forceinline__ uint64_t make_desc(uint32_t addr, uint32_t lbo, uint32_t sbo, uint32_t mode) {
    return (uint64_t)((addr & 0x3FFFF) >> 4) | ((uint64_t)(lbo >> 4) << 16) | ((uint64_t)(sbo >> 4) << 32) | ((uint64_t)mode << 62);
}
__device__ __forceinline__ void wgmma_rs128(float (&d)[64], uint2 hi, uint2 lo, uint64_t db, int acc) {
    asm volatile("{\n.reg .pred p;\nsetp.ne.b32 p, %69, 0;\nwgmma.mma_async.sync.aligned.m64n128k16.f32.bf16.bf16 {%0,%1,%2,%3,%4,%5,%6,%7,%8,%9,%10,%11,%12,%13,%14,%15,%16,%17,%18,%19,%20,%21,%22,%23,%24,%25,%26,%27,%28,%29,%30,%31,%32,%33,%34,%35,%36,%37,%38,%39,%40,%41,%42,%43,%44,%45,%46,%47,%48,%49,%50,%51,%52,%53,%54,%55,%56,%57,%58,%59,%60,%61,%62,%63}, {%64,%65,%66,%67}, %68, p, 1, 1, 0;\n}"
                 : "+f"(d[0]), "+f"(d[1]), "+f"(d[2]), "+f"(d[3]), "+f"(d[4]), "+f"(d[5]), "+f"(d[6]), "+f"(d[7]), "+f"(d[8]), "+f"(d[9]), "+f"(d[10]), "+f"(d[11]), "+f"(d[12]), "+f"(d[13]), "+f"(d[14]), "+f"(d[15]), "+f"(d[16]), "+f"(d[17]), "+f"(d[18]), "+f"(d[19]), "+f"(d[20]), "+f"(d[21]), "+f"(d[22]), "+f"(d[23]), "+f"(d[24]), "+f"(d[25]), "+f"(d[26]), "+f"(d[27]), "+f"(d[28]), "+f"(d[29]), "+f"(d[30]), "+f"(d[31]), "+f"(d[32]), "+f"(d[33]), "+f"(d[34]), "+f"(d[35]), "+f"(d[36]), "+f"(d[37]), "+f"(d[38]), "+f"(d[39]), "+f"(d[40]), "+f"(d[41]), "+f"(d[42]), "+f"(d[43]), "+f"(d[44]), "+f"(d[45]), "+f"(d[46]), "+f"(d[47]), "+f"(d[48]), "+f"(d[49]), "+f"(d[50]), "+f"(d[51]), "+f"(d[52]), "+f"(d[53]), "+f"(d[54]), "+f"(d[55]), "+f"(d[56]), "+f"(d[57]), "+f"(d[58]), "+f"(d[59]), "+f"(d[60]), "+f"(d[61]), "+f"(d[62]), "+f"(d[63])
                 : "r"(hi.x), "r"(hi.y), "r"(lo.x), "r"(lo.y), "l"(db), "r"(acc));
}
template <int V> struct Int { __device__ constexpr operator int() const { return V; } };
__device__ __forceinline__ void sts4(uint32_t a, const uint32_t* v) { asm volatile("st.shared.v4.u32 [%0], {%1,%2,%3,%4};" ::"r"(a), "r"(v[0]), "r"(v[1]), "r"(v[2]), "r"(v[3]) : "memory"); }
__device__ __forceinline__ uint32_t lds1(uint32_t a) { uint32_t v; asm volatile("ld.shared.u32 %0, [%1];" : "=r"(v) : "r"(a) : "memory"); return v; }
__device__ __forceinline__ uint4 lds4(uint32_t a) { uint4 v; asm volatile("ld.shared.v4.u32 {%0,%1,%2,%3}, [%4];" : "=r"(v.x), "=r"(v.y), "=r"(v.z), "=r"(v.w) : "r"(a) : "memory"); return v; }
__device__ __forceinline__ void cv_store(unsigned char* p, uint4 x, uint4 y) {
    asm volatile("st.relaxed.gpu.global.v2.u32 [%0], {%1,%2};" ::"l"(p), "r"(add2(x.x, __byte_perm(y.x, y.y, 0x5410))), "r"(add2(x.y, __byte_perm(y.z, y.w, 0x5410))) : "memory");
    asm volatile("st.relaxed.gpu.global.v2.u32 [%0], {%1,%2};" ::"l"(p + 128), "r"(add2(x.z, __byte_perm(y.x, y.y, 0x7632))), "r"(add2(x.w, __byte_perm(y.z, y.w, 0x7632))) : "memory");
}
__device__ __forceinline__ int usw(int ch) { return ch ^ ((ch >> 3) & 1); }
__global__ void __launch_bounds__(CV_THREADS, 1) conv_kernel(int layer, const uint4* __restrict__ piv, const float4* __restrict__ sum, const bf16* __restrict__ x1T,
                                                             bf16* __restrict__ dst, const uint4* __restrict__ tap, const __grid_constant__ CUtensorMap tmOut) {
    extern __shared__ __align__(1024) unsigned char sm[];
    SPAN(3 + 4 * layer, 0);
    bf16* Us = reinterpret_cast<bf16*>(sm + CV_SM_U);
    bf16* Xs = reinterpret_cast<bf16*>(sm + CV_SM_X);
#define CV_IDX int tid; asm volatile("mov.u32 %0, %tid.x;" : "=r"(tid)); const int lane = tid & 31, warp = __shfl_sync(~0u, tid >> 5, 0);
    const int d0 = blockIdx.x * CV_CPB, tile = blockIdx.x; (void)tile;
    const uint32_t cnt = smem_u32(sm + CV_SM_CNT);
    struct Lc { uint32_t a4, a8, uc, ud, y, e4, en, sp, ss; int go; };
    auto lane_consts = [&](int lane, int c) {
        const int mat = lane >> 3, r = lane & 7, g = lane >> 2, ti = lane & 3, e = g - 2 * ti;
        const int j2 = 13 + (r ^ 1) + 8 * (mat >> 1), j3 = j2 + 2, i0 = 8 * (mat & 1);
        const uint32_t sb = smem_u32(sm), oc = sb + usw(16 * (mat >> 1) + 2 * r + (mat & 1)) * 16;
        const Lc l = {sb + CV_SM_B + c * BX_LEN + ((j2 & 1) ? BX_3 + (4 * j2 + i0 + 84) * 2 : BX_5 + (4 * j2 + i0 + 80) * 2),
                      sb + CV_SM_B + c * BX_LEN + ((j3 & 1) ? BX_7 : BX_9) + (8 * j3 + i0 + 136) * 2,
                      oc + CV_SM_U + (c * ULEN + UPADF) * 2, sb + CV_SM_U + (c * ULEN + UPADF) * 2 + usw(16 * mat + 2 * r + 2) * 16, oc + CV_SM_Y + c * 8192,
                      sb + CV_SM_O + 2048 * c + (307 + 2 * g - ti) * 4, sb + CV_SM_T + c * TAPB + (152 + 144 + e) * 8 + 4,
                      e == -5 ? 0x4410u : e == -4 ? 0x1044u : 0x4444u, e == 3 ? 0x4410u : e == 4 ? 0x1044u : 0x4444u,
                      c * XCP * 2 + (lane >> 4) * 256 + (lane & 15) * 8};
        asm volatile("st.shared.u32 [%0], %1;" ::"r"(l.y), "r"(l.a4 ^ l.a8 ^ l.uc ^ l.ud ^ l.e4 ^ l.en ^ l.sp ^ l.ss ^ l.go) : "memory");
        return l;
    };
    unsigned char* const dq = reinterpret_cast<unsigned char*>(dst + (size_t)d0 * XCP);
    auto far = [&](auto T0_, const auto& seq, const Lc& lc, int c, int lane, const uint2 (&f)[20], uint32_t kk) {
        constexpr int T0 = T0_, T1 = T0 + 6, TC = T0 > 7 ? T0 : 7, NS = sizeof(seq) / sizeof(seq[0]), PD = T0 > 7 ? CV_PDH : CV_PDF;
        uint32_t bq[28], yw[4], yz[4], P, S;
        uint4 xv, yv;
        asm("prmt.b32 %0, %1, 0, %2;" : "=r"(P) : "r"(kk), "r"(lc.sp));
        asm("prmt.b32 %0, %1, 0, %2;" : "=r"(S) : "r"(kk), "r"(lc.ss));
#pragma unroll
        for (int k = 0; 2 * k < T1 - TC + 4; k++) ldsm_x4(bq + 4 * k, lc.uc + (TC - 8) * 256 + 512 * k);
#pragma unroll
        for (int k = 0; 4 * k < T1 - TC; k++) ldsm_x4(bq + 20 + 4 * k, lc.ud + (TC - 8) * 256 + 1024 * k);
        CST(3);
        mbar_wait(cnt + 8 * c, 0);
        mbar_wait(cnt + 40, 0);
        CST(4);
        float acc[6][4] = {};
        uint32_t a[PD + 1][4];
#pragma unroll
        for (int i = -PD; i < NS + 3; i++) {
            if (i + PD < NS) ldsm_x4_t(a[(i + PD) % (PD + 1)], seq[i + PD] < 32 ? lc.a4 + (seq[i + PD] - 2) * 128 : lc.a8 + (seq[i + PD] - 34) * 256);
            if (i < 0) continue;
#pragma unroll
            for (int T = T0; T < T1; T++) {
                if (i >= NS) break;
                const int ee = seq[i] < 32 ? 2 * T - 6 - seq[i] : T + 35 - seq[i];
                if (i == 0 && T >= TC) mma_bf16(acc[T - T0], P, 0u, S, P, bq[2 * (T - TC)], bq[2 * (T - TC) + 1]);
                if (i == 1 && T >= TC) mma_bf16_k8(acc[T - T0], 0u, S, bq[20 + T - TC]);
                if (i == (T >= TC ? 2 : 0)) mma_bf16(acc[T - T0], f[19].x, 0u, f[19].y, f[19].x, bq[2 * (T - TC + 4)], bq[2 * (T - TC + 4) + 1]);
                if (seq[i] < 32 ? ee >= 0 && ee <= 9 : ee >= 10) mma_bf16(acc[T - T0], a[i % (PD + 1)][0], a[i % (PD + 1)][1], a[i % (PD + 1)][2], a[i % (PD + 1)][3], f[ee].x, f[ee].y);
            }
#pragma unroll
            for (int k = 0; k < 3; k++) {
                const int o = 256 * T0 + 512 * k;
                auto at = [&](int d) { return i - d >= 0 && i - d < NS && seq[i - d < 0 ? 0 : i - d < NS ? i - d : 0] == 2 * T0 + 4 * k - 4; };
                if (at(CV_D2)) {
                    cv_store(dq + lc.go + o, xv, yv);
                    if (layer > 19 - 2 * k) __trap();
                }
                if (at(-2)) { ldsm_x4_t(yw, lc.y + o); ldsm_x4_t(yz, lc.y + 3584 + o); }
                if (at(1)) {
#pragma unroll
                    for (int q = 0; q < 4; q++) yw[q] = add2(add2(yw[q], yz[q]), pack2(acc[2 * k + (q >> 1)][2 * (q & 1)], acc[2 * k + (q >> 1)][2 * (q & 1) + 1]));
                    stsm_x4_t(lc.y + o, yw[0], yw[1], yw[2], yw[3]);
                    xv = lds4(smem_u32(Xs + c * XLEN) + o + lane * 16);
                    __syncwarp();
                    yv = lds4(smem_u32(sm + CV_SM_Y) + c * 8192 + o + usw(lane) * 16);
                    if (layer > 20 - 2 * k) __trap();
                    if (k == 2) CST(6);
                }
            }
        }
    };
    TSTAMP1X(9, 256);
    if (threadIdx.x >= 256) {
        CV_IDX
        const int t2 = tid - 256, wgu = (warp >> 2) & 1, g = lane >> 2, ti = lane & 3;
        if (t2 == 0) {
            mbar_init(cnt + 48, 1);
            asm volatile("fence.mbarrier_init.release.cluster;" ::: "memory");
            mbar_expect_tx(cnt + 48, CV_CPB * 2048);
            bulk_load(smem_u32(sm + CV_SM_O), tap + d0 * 128, CV_CPB * 2048, cnt + 48);
        } else if (lane == 0) {
            if (warp < 15) mbar_init(cnt + 8 * (warp - 9), warp == 14 ? 8 : 4);
            else if (layer) prefetch_tmap(&tmOut);
        }
        if (t2 < 140) {
            const int k = t2;
            const int off = k < 20 ? CV_SM_B + BX_5 + 8 * k : k < 40 ? CV_SM_B + BX_3 + 8 * (k - 20) : k < 74 ? CV_SM_B + BX_9 + 8 * (k - 40) : k < 108 ? CV_SM_B + BX_7 + 8 * (k - 74) : CV_SM_U + 8 * (k - 108);
            const int str = k < 108 ? BX_LEN : ULEN * 2;
#pragma unroll
            for (int c = 0; c < CV_CPB; c++) *reinterpret_cast<uint2*>(sm + off + c * str) = make_uint2(0, 0);
        }
        fence_async_smem();
        asm volatile("bar.arrive 3, 512;" ::: "memory");
        asm volatile("bar.sync 1, 256;" ::: "memory");
        TSTAMP1X(10, 256);
        asm volatile("setmaxnreg.inc.sync.aligned.u32 168;");
        const int hc = wgu ? warp & 3 : 4;
        const Lc lc = lane_consts(lane, hc);
        const uint32_t* E2[3];
#pragma unroll
        for (int k = 0; k < 3; k++) {
            const int i = min(t2 + 256 * k, 759), h = i / 76;
            E2[k] = reinterpret_cast<const uint32_t*>(sm + CV_SM_O) + 3 + i + (h >> 1) * 360 + (h & 1) * 52;
        }
        mbar_wait(cnt + 48, 0);
        TSTAMP1X(11, 256);
        {
            uint32_t w[3][4];
#pragma unroll
            for (int k = 0; k < 3; k++) { w[k][0] = E2[k][0]; w[k][1] = E2[k][1]; w[k][2] = E2[k][64]; w[k][3] = E2[k][65]; }
#pragma unroll
            for (int k = 0; k < 3; k++)
                *reinterpret_cast<uint4*>(sm + CV_SM_T + min(t2 + 256 * k, 759) * 16) =
                    make_uint4(__byte_perm(w[k][1], w[k][0], 0x7610), __byte_perm(w[k][3], w[k][2], 0x7610), __byte_perm(w[k][1], 0, 0x1032), __byte_perm(w[k][3], 0, 0x1032));
        }
        asm volatile("bar.sync 1, 256;" ::: "memory");
        const uint2* Tc = reinterpret_cast<const uint2*>(sm + CV_SM_T) + 16 + 76 * (warp & 2) + 8 * (warp & 1) + g - 2 * ti;
        uint2 fa[8][2], fn[8][2];
        auto near_taps = [&](uint2 (&f)[8][2], int c) {
#pragma unroll
            for (int m = 0; m < 8; m++) { f[m][0] = Tc[c * (TAPB / 8) + 16 * m]; f[m][1] = Tc[c * (TAPB / 8) + 16 * m - 8]; }
        };
        near_taps(fa, 3 * wgu);
        near_taps(fn, 2 - wgu);
        TSTAMP1X(12, 256); CST(0);
        uint32_t ya = smem_u32(sm + CV_SM_Y) + wgu * 8192 + (warp & 2) * 2048 + usw(2 * lane + (warp & 1)) * 16;
        uint64_t db = make_desc(smem_u32(Us + wgu * ULEN + UPADF), 16, 256, 3);
        if (wgu) asm volatile("bar.sync 6, 384;" ::: "memory");
        int c = wgu;
        auto chain = [&](const uint2 (&f)[8][2], auto&& meanwhile) {
            float acc[64];
            asm volatile("bar.sync %0, %1;" ::"r"(c ? 4 + wgu : 2), "r"(c ? 256 : 384) : "memory");
            TSTAMPC(1 + 3 * c);
            wgmma_fence();
#pragma unroll
            for (int m = 0; m < 8; m++) {
                wgmma_rs128(acc, f[m][0], f[m][1], db - (uint64_t)(2 * m), m);
                if (m == CV_HAND && c < 4) asm volatile("bar.arrive %0, 256;" ::"r"(5 - wgu) : "memory");
            }
            wgmma_commit();
            asm volatile("griddepcontrol.launch_dependents;" ::: "memory");
            TSTAMPC(2 + 3 * c); CST(13 + (c >> 1));
            meanwhile();
            wgmma_wait<0>();
            TSTAMPC(3 + 3 * c); CST(10 + (c >> 1));
            uint32_t w[16];
#pragma unroll
            for (int j = 0; j < 16; j++) w[j] = j ? pack2(acc[4 * j] + acc[4 * j - 2], acc[4 * j + 1] + acc[4 * j - 1]) : pack2(acc[0], acc[1]);
#pragma unroll
            for (int j = 0; j < 16; j += 4) stsm_x4_t(ya + 256 * j, w[j], w[j + 1], w[j + 2], w[j + 3]);
            __syncwarp();
            if (lane == 0) mbar_arrive(cnt + 8 * c);
            c += 2; ya += 16384; db += ULEN / 4;
        };
        const uint32_t e4 = lc.e4, e8 = e4 + 428 - 4 * g;
        uint2 fl[4];
        uint32_t kk;
#pragma unroll 1
        for (;;) {
            if (c != 1) chain(fa, [&] {
                if (c == 3 || warp + c == 12) {
#pragma unroll
                    for (int k = 0; k < 19; k++) (k < 16 ? fn[(k >> 1) & 7][k & 1] : fl[k & 3]) = make_uint2(lds1(k < 10 ? e4 + 32 * k + 16 : e8 + 32 * k - 304), lds1(k < 10 ? e4 + 32 * k : e8 + 32 * k - 320));
                    fl[3] = make_uint2(lds1(lc.en), lds1(lc.en - 64));
                    kk = lds1(smem_u32(sm + CV_SM_O) + 2048 * hc + 1672);
                }
            });
            if (c > 4) break;
            if (c == 2) asm volatile("bar.sync 7, 384;" ::: "memory");
            chain(fn, [&] { if (c == 2) near_taps(fa, 4); });
        }
        TSTAMP1X(6, 256); CST(2);
        if (wgu || warp == 8) {
            constexpr int seq[29] = {5, 6, 32, 7, 33, 8, 34, 9, 35, 10, 36, 11, 12, 13, 14, 15, 16, 17, 37, 18, 38, 19, 20, 21, 39, 22, 40, 23, 24};
            uint2 f[20];
#pragma unroll
            for (int k = 0; k < 20; k++) f[k] = k < 16 ? fn[(k >> 1) & 7][k & 1] : fl[k & 3];
            far(Int<10>(), seq, lc, hc, lane, f, kk);
        }
    } else {
        asm volatile("setmaxnreg.dec.sync.aligned.u32 88;");
        CV_IDX
        const uint4* ppv = piv + tid;
        const float4* psv = sum + tid;
        const uint2* pxv = reinterpret_cast<const uint2*>(x1T + (size_t)d0 * XCP) + (tid >> 4) * 32 + (tid & 15);
        asm volatile("st.shared.u64 [%0], %1;" ::"r"(smem_u32(Xs) + tid * 16), "l"((uint64_t)ppv ^ (uint64_t)psv ^ (uint64_t)pxv) : "memory");
        const int tc = (0x04302100 >> (4 * warp)) & 7;
        const Lc lc = lane_consts(lane, tc);
        pdl_sync();
        SPAN(3 + 4 * layer, 1);
        TSTAMP(0); CST(0);
        if (tid == 0) TSTAMPC(0);
        if (threadIdx.x == 0) { GSTAMP(g_tim, 15); }
        float4 sv[4];
#pragma unroll
        for (int k = 0; k < 4; k++)
            asm volatile("ld.relaxed.gpu.global.v4.f32 {%0,%1,%2,%3}, [%4];" : "=f"(sv[k].x), "=f"(sv[k].y), "=f"(sv[k].z), "=f"(sv[k].w) : "l"(psv + 256 * k) : "memory");
        uint4 pv;
        asm volatile("ld.relaxed.gpu.global.v4.u32 {%0,%1,%2,%3}, [%4];" : "=r"(pv.x), "=r"(pv.y), "=r"(pv.z), "=r"(pv.w) : "l"(ppv) : "memory");
        uint2 xe[CV_CPB], xo[CV_CPB];
#pragma unroll
        for (int c = 0; c < CV_CPB; c++) {
            asm volatile("ld.relaxed.gpu.global.v2.u32 {%0,%1}, [%2];" : "=r"(xe[c].x), "=r"(xe[c].y) : "l"(pxv + c * (XCP / 4)) : "memory");
            asm volatile("ld.relaxed.gpu.global.v2.u32 {%0,%1}, [%2];" : "=r"(xo[c].x), "=r"(xo[c].y) : "l"(pxv + c * (XCP / 4) + 16) : "memory");
        }
        constexpr float idm = 1.0f / DM;
        uint32_t mw[4];
        float rs[8];
#pragma unroll
        for (int k = 0; k < 4; k++) {
            const uint32_t pw = k == 0 ? pv.x : k == 1 ? pv.y : k == 2 ? pv.z : pv.w;
            const float d0_ = sv[k].x * idm, d1_ = sv[k].z * idm;
            mw[k] = pack2(__uint_as_float(pw << 16) + d0_, __uint_as_float(pw & 0xffff0000u) + d1_);
            const uint32_t vr = pack2(fmaxf(fmaf(-d0_, d0_, sv[k].y * idm), 0.f), fmaxf(fmaf(-d1_, d1_, sv[k].w * idm), 0.f));
            const uint32_t ve = pack2(__uint_as_float(vr << 16) + 1e-5f, __uint_as_float(vr & 0xffff0000u) + 1e-5f);
            const uint32_t sd = pack2(sqrt_apx(__uint_as_float(ve << 16)), sqrt_apx(__uint_as_float(ve & 0xffff0000u)));
            rs[2 * k] = rcp_apx(__uint_as_float(sd << 16)); rs[2 * k + 1] = rcp_apx(__uint_as_float(sd & 0xffff0000u));
        }
        if (rs[0] != 123.f) TSTAMP(13);
        const uint32_t ua = smem_u32(Us) + usw(tid + UPADF / 8) * 16;
        uint32_t uw[CV_CPB][4];
#pragma unroll
        for (int c = 0; c < CV_CPB; c++) {
            const uint32_t e0 = sub2(xe[c].x, mw[0]), e1 = sub2(xe[c].y, mw[1]), o0 = sub2(xo[c].x, mw[2]), o1 = sub2(xo[c].y, mw[3]);
            uw[c][0] = pack2(__uint_as_float(e0 << 16) * rs[0], __uint_as_float(o0 << 16) * rs[4]); uw[c][1] = pack2(__uint_as_float(e0 & 0xffff0000u) * rs[1], __uint_as_float(o0 & 0xffff0000u) * rs[5]);
            uw[c][2] = pack2(__uint_as_float(e1 << 16) * rs[2], __uint_as_float(o1 << 16) * rs[6]); uw[c][3] = pack2(__uint_as_float(e1 & 0xffff0000u) * rs[3], __uint_as_float(o1 & 0xffff0000u) * rs[7]);
            asm volatile("st.shared.v4.u32 [%0], {%1,%2,%3,%4};" ::"r"(ua + c * ULEN * 2), "r"(uw[c][0]), "r"(uw[c][1]), "r"(uw[c][2]), "r"(uw[c][3]) : "memory");
            if (c < 2) {
                fence_async_smem();
                asm volatile("bar.arrive %0, 384;" ::"r"(2 + 4 * c) : "memory");
                if (layer > 29 - c) __trap();
            }
        }
        fence_async_smem();
#pragma unroll
        for (int c = 0; c < CV_CPB; c++) *reinterpret_cast<uint4*>(Xs + c * XLEN + tid * 8) = make_uint4(xe[c].x, xe[c].y, xo[c].x, xo[c].y);
        asm volatile("bar.arrive 7, 384;" ::: "memory");
        asm volatile("bar.sync 3, 512;" ::: "memory");
        TSTAMP(1); CST(1);
        {
            auto box = [&](auto c0, auto c1, int chunk, int cb, bool full) {
                const uint32_t ea = smem_u32(Us + cb * ULEN) + usw(chunk + UPADF / 8 + (lane ? 1 : -1)) * 16, bx = smem_u32(sm + CV_SM_B + cb * BX_LEN) + chunk * 16;
                uint32_t lo[CV_CPB][4], hi[CV_CPB][2];
#pragma unroll
                for (int c = c0; c < c1; c++) {
                    lo[c][0] = 0;
#pragma unroll
                    for (int k = 1; k < 4; k++) lo[c][k] = __shfl_up_sync(~0u, uw[c][k], 1);
#pragma unroll
                    for (int k = 0; k < 2; k++) hi[c][k] = __shfl_down_sync(~0u, uw[c][k], 1);
                }
#pragma unroll
                for (int c = c0; c < c1; c++)
                    asm volatile("{\n.reg .pred p, q;\nsetp.eq.s32 p, %7, 0;\nsetp.eq.s32 q, %7, 31;\n@p ld.shared.v4.u32 {%0,%1,%2,%3}, [%6];\n@q ld.shared.v2.u32 {%4,%5}, [%6];\n}"
                                 : "+r"(lo[c][0]), "+r"(lo[c][1]), "+r"(lo[c][2]), "+r"(lo[c][3]), "+r"(hi[c][0]), "+r"(hi[c][1]) : "r"(ea + c * ULEN * 2), "r"(lane) : "memory");
#pragma unroll
                for (int c = c0; c < c1; c++) {
                    const uint32_t e[9] = {lo[c][1], lo[c][2], lo[c][3], uw[c][0], uw[c][1], uw[c][2], uw[c][3], hi[c][0], hi[c][1]};
                    uint32_t o[8], p[8], t[7], b3[5], b5[7];
#pragma unroll
                    for (int i = 0; i < 8; i++) { o[i] = __byte_perm(e[i], e[i + 1], 0x5432); p[i] = add2(e[i], o[i]); }
#pragma unroll
                    for (int i = 0; i < 5; i++) b3[i] = add2(o[i], p[i + 1]);
                    sts4(bx + c * BX_LEN + BX_3 + 160, b3);
#pragma unroll
                    for (int i = 1; i < 7; i++) { t[i] = add2(p[i], p[i + 1]); b5[i] = add2(t[i], e[i + 2]); }
                    sts4(bx + c * BX_LEN + BX_5 + 160, b5 + 2);
                    if (full) {
#pragma unroll
                        for (int i = 1; i < 5; i++) { b3[i] = add2(b3[i], t[i + 2]); t[i] = add2(t[i], b5[i + 2]); }
                        sts4(bx + c * BX_LEN + BX_7 + 272, b3 + 1);
                        sts4(bx + c * BX_LEN + BX_9 + 272, t + 1);
                    }
                }
            };
            auto reload = [&](int c, uint32_t a) { const uint4 v = lds4(a); uw[c][0] = v.x; uw[c][1] = v.y; uw[c][2] = v.z; uw[c][3] = v.w; };
            if (warp >= 6) {
#pragma unroll
                for (int c = 0; c < 3; c++) reload(c, ua - 1024 + (c + 2) * ULEN * 2);
            }
            if (warp >= 4) {
#pragma unroll
                for (int c = 3; c < 5; c++) reload(c, ua - 2048 + c * ULEN * 2);
            }
            box(Int<0>(), Int<3>(), warp < 6 ? tid : tid - 64, warp < 6 ? 0 : 2, warp < 4);
            if (warp >= 4) box(Int<3>(), Int<5>(), tid - 128, 0, true);
            else if (tid >= 128 - CV_CPB) {
                const int c = 127 - tid;
                const uint2 v = *reinterpret_cast<const uint2*>(Us + c * ULEN + UPADF);
                const float s1 = __uint_as_float(v.x << 16), s2 = s1 + __uint_as_float(v.x & 0xffff0000u), s3 = s2 + __uint_as_float(v.y << 16), s4 = s3 + __uint_as_float(v.y & 0xffff0000u);
                unsigned char* bc = sm + CV_SM_B + c * BX_LEN;
                *reinterpret_cast<uint32_t*>(bc + BX_5 + 156) = pack2(s1, s2);
                *reinterpret_cast<uint2*>(bc + BX_7 + 264) = make_uint2(v.x << 16, pack2(s2, s3));
                *reinterpret_cast<uint2*>(bc + BX_9 + 264) = make_uint2(pack2(s1, s2), pack2(s3, s4));
            }
        }
        __syncwarp();
        if (lane == 0) mbar_arrive(cnt + 40);
        TSTAMP(2); CST(2);
        if (layer && blockIdx.x == 0 && tid == 224) g_epoch = ld_epoch();
        __syncwarp();
        if ((0x6e >> warp) & 1) {
            constexpr int seq[16] = {0, 1, 2, 3, 4, 5, 6, 32, 7, 8, 9, 33, 10, 34, 11, 12};
            uint2 f[20];
            mbar_wait(cnt, 0);
            const uint32_t e8 = lc.e4 + 428 - (lane & 28);
#pragma unroll
            for (int k = 0; k < 13; k++) f[k] = make_uint2(lds1(k < 10 ? lc.e4 + 32 * k + 16 : e8 + 32 * k - 304), lds1(k < 10 ? lc.e4 + 32 * k : e8 + 32 * k - 320));
            f[19] = make_uint2(lds1(lc.en), lds1(lc.en - 64));
            far(Int<4>(), seq, lc, tc, lane, f, lds1(smem_u32(sm + CV_SM_O) + 2048 * tc + 1672));
        }
    }
    {
        CV_IDX
        if ((0xc91 >> warp) & 1) {
            const int c = __popc(0xc91 & ((1 << warp) - 1));
            uint4 xv[2], yv[2];
#pragma unroll
            for (int k = 0; k < 2; k++) xv[k] = lds4(smem_u32(Xs + c * XLEN) + 512 * k + lane * 16);
            const uint32_t u0 = lds1(smem_u32(Us + c * ULEN) + (lane == 31 ? UPADF * 2 : 0));
            mbar_wait(cnt + 8 * c, 0);
#pragma unroll
            for (int k = 0; k < 2; k++) yv[k] = lds4(smem_u32(sm + CV_SM_Y) + c * 8192 + 512 * k + usw(lane) * 16);
            const uint4 yz = lds4(smem_u32(sm + CV_SM_Y) + c * 8192 + 4096 + usw(lane) * 16);
            const float kk = __uint_as_float(lds1(smem_u32(sm + CV_SM_O) + 2048 * c + 1272) << 16);
            yv[1].x = add2(yv[1].x, yz.x); yv[1].y = add2(yv[1].y, yz.y); yv[1].z = add2(yv[1].z, yz.z);
            yv[1].w = pack2(fmaf(kk, __uint_as_float(u0 << 16), __uint_as_float(yv[1].w << 16) + __uint_as_float(yz.w << 16)),
                            fmaf(kk, __uint_as_float(u0 << 16) + __uint_as_float(u0 & 0xffff0000u), __uint_as_float(yv[1].w & 0xffff0000u) + __uint_as_float(yz.w & 0xffff0000u)));
#pragma unroll
            for (int k = 0; k < 2; k++) cv_store(dq + c * XCP * 2 + (lane >> 4) * 256 + (lane & 15) * 8 + 512 * k, xv[k], yv[k]);
        }
        TSTAMP(4); CST(8);
        if (layer == 1) {
            const int mb = blockIdx.x >> 3, cg = blockIdx.x & 7;
            const bf16* src = dst + (size_t)(cg * 80 + (tid >> 4)) * XCP + mb * 128 + (tid & 15) * 8;
            uint32_t v[3][4];
            __syncthreads();
            uint32_t todo = warp < 8 ? 7 : 3;
#pragma unroll 1
            for (int it = 0; it < SPIN_MAX; it++) {
#pragma unroll
                for (int k = 0; k < 3; k++)
                    if (todo >> k & 1)
                        asm volatile("ld.relaxed.gpu.global.v4.u32 {%0,%1,%2,%3}, [%4];" : "=r"(v[k][0]), "=r"(v[k][1]), "=r"(v[k][2]), "=r"(v[k][3]) : "l"(src + k * (32 * XCP)) : "memory");
#pragma unroll
                for (int k = 0; k < 3; k++)
                    if ((todo >> k & 1) && v[k][0] != ~0u && v[k][1] != ~0u && v[k][2] != ~0u && v[k][3] != ~0u) {
                        *reinterpret_cast<uint4*>(sm + (32 * k + (tid >> 4)) * 272 + (tid & 15) * 16) = make_uint4(v[k][0], v[k][1], v[k][2], v[k][3]);
                        todo ^= 1u << k;
                    }
                if (!todo) break;
                __nanosleep(CV_SLEEP);
            }
            __syncthreads();
            uint32_t w[12];
#pragma unroll
            for (int k = 0; k < 3; k++) ldsm_x4(&w[4 * k], smem_u32(sm) + min(32 * k + lane, 79) * 272 + warp * 16);
            const uint32_t ot = smem_u32(sm + CV_SM_O) + warp * 1280, oa = ot + (lane & 7) * 160 + (lane >> 3) * 16;
            stsm_x4_t(oa, w[0], w[1], w[2], w[3]);
            stsm_x4_t(oa + 64, w[4], w[5], w[6], w[7]);
            asm volatile("stmatrix.sync.aligned.m8n8.x2.trans.shared.b16 [%0], {%1,%2};" ::"r"(oa + 128), "r"(w[8]), "r"(w[9]) : "memory");
            fence_async_smem();
            __syncwarp();
            if (lane == 0) {
                asm volatile("cp.async.bulk.tensor.3d.global.shared::cta.bulk_group [%0, {%1, %2, %3}], [%4];" ::"l"(&tmOut), "r"(cg * 80), "r"(mb * 64 + 8 * (warp & 7)), "r"(warp >> 3), "r"(ot) : "memory");
                asm volatile("cp.async.bulk.commit_group;" ::: "memory");
                asm volatile("cp.async.bulk.wait_group.read 0;" ::: "memory");
            }
        }
    }
    TSTAMP(3); CST(9); CST_END;
    GSTAMP(g_tim, 14);
    SPAN(3 + 4 * layer, 3);
}

template <int TA, int TB>
__device__ __forceinline__ void wgmma_n240(float (&d)[120], uint64_t da, uint64_t db, int acc) {
    asm volatile("{\n.reg .pred p;\nsetp.ne.b32 p, %124, 0;\nwgmma.mma_async.sync.aligned.m64n240k16.f32.bf16.bf16 {%0,%1,%2,%3,%4,%5,%6,%7,%8,%9,%10,%11,%12,%13,%14,%15,%16,%17,%18,%19,%20,%21,%22,%23,%24,%25,%26,%27,%28,%29,%30,%31,%32,%33,%34,%35,%36,%37,%38,%39,%40,%41,%42,%43,%44,%45,%46,%47,%48,%49,%50,%51,%52,%53,%54,%55,%56,%57,%58,%59,%60,%61,%62,%63,%64,%65,%66,%67,%68,%69,%70,%71,%72,%73,%74,%75,%76,%77,%78,%79,%80,%81,%82,%83,%84,%85,%86,%87,%88,%89,%90,%91,%92,%93,%94,%95,%96,%97,%98,%99,%100,%101,%102,%103,%104,%105,%106,%107,%108,%109,%110,%111,%112,%113,%114,%115,%116,%117,%118,%119}, %120, %121, p, 1, 1, %122, %123;\n}"
                 : "+f"(d[0]), "+f"(d[1]), "+f"(d[2]), "+f"(d[3]), "+f"(d[4]), "+f"(d[5]), "+f"(d[6]), "+f"(d[7]), "+f"(d[8]), "+f"(d[9]), "+f"(d[10]), "+f"(d[11]), "+f"(d[12]), "+f"(d[13]), "+f"(d[14]), "+f"(d[15]), "+f"(d[16]), "+f"(d[17]), "+f"(d[18]), "+f"(d[19]), "+f"(d[20]), "+f"(d[21]), "+f"(d[22]), "+f"(d[23]), "+f"(d[24]), "+f"(d[25]), "+f"(d[26]), "+f"(d[27]), "+f"(d[28]), "+f"(d[29]), "+f"(d[30]), "+f"(d[31]), "+f"(d[32]), "+f"(d[33]), "+f"(d[34]), "+f"(d[35]), "+f"(d[36]), "+f"(d[37]), "+f"(d[38]), "+f"(d[39]), "+f"(d[40]), "+f"(d[41]), "+f"(d[42]), "+f"(d[43]), "+f"(d[44]), "+f"(d[45]), "+f"(d[46]), "+f"(d[47]), "+f"(d[48]), "+f"(d[49]), "+f"(d[50]), "+f"(d[51]), "+f"(d[52]), "+f"(d[53]), "+f"(d[54]), "+f"(d[55]), "+f"(d[56]), "+f"(d[57]), "+f"(d[58]), "+f"(d[59]), "+f"(d[60]), "+f"(d[61]), "+f"(d[62]), "+f"(d[63]), "+f"(d[64]), "+f"(d[65]), "+f"(d[66]), "+f"(d[67]), "+f"(d[68]), "+f"(d[69]), "+f"(d[70]), "+f"(d[71]), "+f"(d[72]), "+f"(d[73]), "+f"(d[74]), "+f"(d[75]), "+f"(d[76]), "+f"(d[77]), "+f"(d[78]), "+f"(d[79]), "+f"(d[80]), "+f"(d[81]), "+f"(d[82]), "+f"(d[83]), "+f"(d[84]), "+f"(d[85]), "+f"(d[86]), "+f"(d[87]), "+f"(d[88]), "+f"(d[89]), "+f"(d[90]), "+f"(d[91]), "+f"(d[92]), "+f"(d[93]), "+f"(d[94]), "+f"(d[95]), "+f"(d[96]), "+f"(d[97]), "+f"(d[98]), "+f"(d[99]), "+f"(d[100]), "+f"(d[101]), "+f"(d[102]), "+f"(d[103]), "+f"(d[104]), "+f"(d[105]), "+f"(d[106]), "+f"(d[107]), "+f"(d[108]), "+f"(d[109]), "+f"(d[110]), "+f"(d[111]), "+f"(d[112]), "+f"(d[113]), "+f"(d[114]), "+f"(d[115]), "+f"(d[116]), "+f"(d[117]), "+f"(d[118]), "+f"(d[119])
                 : "l"(da), "l"(db), "n"(TA), "n"(TB), "r"(acc));
}

__device__ __forceinline__ void wgmma_n80(float (&d)[40], uint64_t da, uint64_t db, int acc) {
    asm volatile("{\n.reg .pred p;\nsetp.ne.b32 p, %42, 0;\nwgmma.mma_async.sync.aligned.m64n80k16.f32.bf16.bf16 {%0,%1,%2,%3,%4,%5,%6,%7,%8,%9,%10,%11,%12,%13,%14,%15,%16,%17,%18,%19,%20,%21,%22,%23,%24,%25,%26,%27,%28,%29,%30,%31,%32,%33,%34,%35,%36,%37,%38,%39}, %40, %41, p, 1, 1, 0, 1;\n}"
                 : "+f"(d[0]), "+f"(d[1]), "+f"(d[2]), "+f"(d[3]), "+f"(d[4]), "+f"(d[5]), "+f"(d[6]), "+f"(d[7]), "+f"(d[8]), "+f"(d[9]), "+f"(d[10]), "+f"(d[11]), "+f"(d[12]), "+f"(d[13]), "+f"(d[14]), "+f"(d[15]), "+f"(d[16]), "+f"(d[17]), "+f"(d[18]), "+f"(d[19]), "+f"(d[20]), "+f"(d[21]), "+f"(d[22]), "+f"(d[23]), "+f"(d[24]), "+f"(d[25]), "+f"(d[26]), "+f"(d[27]), "+f"(d[28]), "+f"(d[29]), "+f"(d[30]), "+f"(d[31]), "+f"(d[32]), "+f"(d[33]), "+f"(d[34]), "+f"(d[35]), "+f"(d[36]), "+f"(d[37]), "+f"(d[38]), "+f"(d[39])
                 : "l"(da), "l"(db), "r"(acc));
}

constexpr int A1_THREADS = 384;
constexpr int A1_NST = 4;
#define A1_SKEW 8
constexpr int A1_STAGE = 16384 + WQ_STAGE;
constexpr int A1_KVP = 336;
constexpr int A1_SM_KV = 2 * A1_STAGE;
constexpr int A1_SM_BAR = A1_NST * A1_STAGE;
constexpr int A1_SM_RS = A1_SM_BAR + 512;
constexpr int A1_SM_W0 = A1_SM_BAR + 3072, A1_SM_W3 = A1_SM_BAR - 3 * WOB, A1_SM_A1 = 2 * WOB, A1_SM_A0 = A1_SM_A1 + 61440;
constexpr int A1_SM_XA = A1_SM_W0 + 2 * WOB, A1_SM_XB = A1_SM_XA + 2048;
constexpr int A1_SMEM = A1_SM_W0 + 3 * WOB;
static_assert(A1_SM_W3 >= A1_SM_KV + 144 * A1_KVP && A1_SM_W3 % 512 == 0 && A1_SM_A1 % 1024 == 0 && A1_SM_A0 <= A1_SM_KV && A1_SM_A0 + 61440 <= A1_SM_W3 && A1_SMEM <= 232448, "layout");
__device__ __forceinline__ constexpr uint32_t wo_off(int h) { return h * WOB + (h < 3 ? A1_SM_W0 : h < 6 ? A1_SM_W3 - 3 * WOB : -6 * WOB); }
#define A1_FRED "red.relaxed.gpu.global.add.u32"
#define A1_FLD "ld.acquire.gpu.global.u32"
#define ST_SLEEP 20
#define ST_SLEEP0 300
#define WO_LATE bar_done
#define A1_P0 2
#define A1_PW (kb - 2)
#define A1_FSPIN SPIN_MAX
#define A1_FSLEEP 40
#define YT_LAYER 1
#define A1_WOAT 6

template <int L>
__device__ __forceinline__ void a1_mainloop(float (&acc)[120], uint32_t sbase, uint32_t bars, int wg, int tile) {
    constexpr int layer = L; (void)layer;
    const uint64_t da0 = L ? make_desc(sbase + wg * 8192, 8192, 1024, 1) : make_desc(sbase + wg * 8192, 16, 1024, 1), db0 = make_desc(sbase + 16384, 1024, 256, 3);
#pragma unroll 1
    for (int t = 0;; t++) {
        const int st = t % A1_NST;
        mbar_wait(bars + 8 * st, (t / A1_NST) & 1);
        if (t == A1_SKEW && wg == 0) mbar_wait(bars + 160, 0);
        TSTAMP3(1 + t);
        wgmma_fence();
#pragma unroll
        for (int kk = 0; kk < 4; kk++) wgmma_n240<L, 1>(acc, da0 + (uint32_t)(st * (A1_STAGE / 16) + kk * (L ? 128 : 2)), db0 + (uint32_t)(st * (A1_STAGE / 16) + (kk >> 1) * (WQ_STAGE / 32) + (kk & 1) * 32), kk ? 1 : t);
        wgmma_commit();
        if (t == 9) break;
        if (t == A1_SKEW - 1 && wg == 0) wgmma_wait<0>(); else wgmma_wait<1>();
        if (t > 0 && (threadIdx.x & 127) == 0) {
            if (t != A1_SKEW || wg) mbar_arrive(bars + 8 * (A1_NST + (t - 1) % A1_NST));
            if (t == A1_SKEW - 1 && wg == 0) mbar_arrive(bars + 8 * (A1_NST + t % A1_NST));
        }
    }
}

__global__ void __launch_bounds__(A1_THREADS, 1) a1_kernel(const int layer, const bf16* __restrict__ x0, const unsigned char* __restrict__ wq, const unsigned char* __restrict__ wo,
                                                           float2* __restrict__ rsum, uint4* __restrict__ of, const __grid_constant__ CUtensorMap tmX,
                                                           const __grid_constant__ CUtensorMap tmR, const __grid_constant__ CUtensorMap tmX1, const __grid_constant__ TileTab tab) {
    extern __shared__ __align__(1024) unsigned char stg[];
    const uint32_t sbase = smem_u32(stg);
    const uint32_t bars = sbase + A1_SM_BAR;
    const uint32_t bar_stat = bars + 64, bar_kv = bars + 72, bar_rd = bars + 168;
    const uint32_t bar_wo = bars + 208, bar_done = bars + 216, bar_pv = bars + 224, bar_kvf = bars + 232, bar_f2 = bars + 248, bar_e2 = bars + 384, que = bars + 448;
    const int tid = threadIdx.x;
    const int w = __shfl_sync(~0u, tid >> 5, 0), wg = w >> 2;
    uint32_t smid, ns;
    asm volatile("mov.u32 %0, %smid;" : "=r"(smid));
    asm volatile("mov.u32 %0, %nsmid;" : "=r"(ns));
    const auto te = tab.e[ns == tab.ns ? smid : 132 + blockIdx.x];
    const int tile = te.tile, mb = te.mb, hg = te.hg;
    float2* rst = reinterpret_cast<float2*>(stg + A1_SM_RS) + 8;
    auto issue_w = [&](int it) { bulk_load(sbase + (it % A1_NST) * A1_STAGE + 16384, wq + te.woff + it * WQ_STAGE, WQ_STAGE, bars + 8 * (it % A1_NST)); };
    auto issue_x = [&](int it, int kb) {
        asm volatile("cp.async.bulk.tensor.5d.shared::cluster.global.mbarrier::complete_tx::bytes [%0], [%1, {%3, %3, %3, %4, %5}], [%2];"
                     ::"r"(sbase + (it % A1_NST) * A1_STAGE), "l"(&tmX), "r"(bars + 8 * (it % A1_NST)), "r"(0), "r"(mb), "r"(kb) : "memory");
    };
    if (w == 8 && tile < 128) {
        const bool one = elect();
        if (one) {
#pragma unroll
            for (int i = 0; i < A1_NST; i++) mbar_init(bars + 8 * i, 1);
            asm volatile("fence.mbarrier_init.release.cluster;" ::: "memory");
        }
        __syncwarp();
        asm volatile("bar.arrive 0, 384;" ::: "memory");
        if (one) {
#define PW asm volatile("griddepcontrol.wait;" ::: "memory");
            if (layer) { issue_w(0); PW issue_x(0, te.kb0); issue_x(1, te.kb0 + 1); }
            else { issue_x(0, te.kb0); issue_x(1, te.kb0 + 1); PW issue_w(0); }
            issue_w(1);
#pragma unroll
            for (int i = 0; i < A1_NST; i++) mbar_expect_tx(bars + 8 * i, A1_STAGE);
            asm volatile("griddepcontrol.launch_dependents;" ::: "memory");
#pragma unroll
            for (int kb = 2; kb < A1_P0; kb++) { issue_x(kb, te.kb0 + kb); issue_w(kb); }
            DBGC(34); DBGV(33, smid); DBGV(40, t_entry); DBGV(30, t_a); DBGV(31, t_b); DBGV(32, t_c); DBGV(38, t_d); DBGV(39, t_e);
        }
    }
    if (tile >= 128) { sm_idle(layer); return; }
    if (wg == 2) {
        if (w != 8) {
            if (tid == 320) { prefetch_tmap(&tmX); prefetch_tmap(&tmR); prefetch_tmap(&tmX1); }
            asm volatile("bar.sync 0, 384;" ::: "memory");
        }
        if (w == 9) {
            asm volatile("bar.arrive 3, 64;" ::: "memory");
            if (layer == 0) pdl_sync();
            float4 a[2] = {};
#pragma unroll
            for (int k = 0; k < 10; k++)
#pragma unroll
                for (int h = 0; h < 2; h++) {
                    const int c4 = min(tid - 288 + 32 * h, 59);
                    const float4 v = __ldcg(reinterpret_cast<const float4*>(g_csp + k * 1920 + hg * 80) + c4 + (c4 / 20) * 140);
                    a[h].x += v.x; a[h].y += v.y; a[h].z += v.z; a[h].w += v.w;
                }
#pragma unroll
            for (int h = 0; h < 2; h++)
#pragma unroll
                for (int k = 0; k < 4; k++) {
                    const float c = 0.5f * (k == 0 ? a[h].x : k == 1 ? a[h].y : k == 2 ? a[h].z : a[h].w), c1 = c - rbf(c), c2 = c1 - rbf(c1);
                    *reinterpret_cast<uint4*>(stg + A1_SM_XB + (4 * min(tid - 288 + 32 * h, 59) + k) * 16) = make_uint4(pack2(c, c1), pack2(c2, 0.f), 0u, 0u);
                }
            fence_async_smem();
            __syncwarp();
            if (tid == 288) mbar_arrive(bar_stat);
#pragma unroll 4
            for (int k = 0; k < 40; k++) asm volatile("st.global.v4.u32 [%0], {%1,%1,%1,%1};" ::"l"(of + (mb * 8 + hg) * 1280 + 32 * k + (tid - 288)), "r"(~0u) : "memory");
            asm volatile("fence.acq_rel.gpu;" ::: "memory");
            asm volatile("fence.proxy.async.global;" ::: "memory");
            __syncwarp();
            if (tid == 288) mbar_arrive(bar_done);
            if (layer == YT_LAYER) {
#pragma unroll 4
                for (int k = tid - 288; k < 5 * XCP / 8; k += 32) asm volatile("st.global.v4.u32 [%0], {%1,%1,%1,%1};" ::"l"(reinterpret_cast<uint4*>(g_yT) + tile * (5 * XCP / 8) + k), "r"(~0u) : "memory");
            }
            TSTAMP1T(9, 288);
        } else if (w == 8) {
            asm volatile("bar.sync 3, 64;" ::: "memory");
            if (elect()) {
#pragma unroll 1
                for (int kb = A1_P0; kb < 10; kb++) {
                    if (kb < A1_NST) mbar_wait(bars + 8 * A1_PW, 0);
                    else {
                        mbar_wait(bars + 8 * (A1_NST + kb % A1_NST), ((kb / A1_NST) - 1) & 1);
                        if (layer && kb < 9) mbar_wait(bar_rd + 8 * (kb - A1_NST), 0);
                        mbar_expect_tx(bars + 8 * (kb % A1_NST), A1_STAGE);
                    }
                    issue_x(kb, kb < 5 ? kb + te.kb0 : kb - te.kb0); issue_w(kb);
                    if (kb == A1_WOAT) {
                        mbar_expect_tx(bar_wo, 8 * WOB);
                        bulk_load(sbase + A1_SM_W0, wo + hg * 8 * WOB, 2 * WOB, bar_wo);
                    }
                }
                TSTAMP1T(6, 256);
                mbar_wait(bars + 8 * (A1_NST + 3), 1);
                bulk_load(sbase + A1_SM_W3, wo + (hg * 8 + 3) * WOB, 3 * WOB, bar_wo);
            }
            __syncwarp();
        } else {
            const int j = tid - 320;
            const uint32_t tag = ld_epoch();
            if (tid == 352) sm_started(layer);
            if (layer == 0) {
                const uint4* src = reinterpret_cast<const uint4*>(x0 + (size_t)(mb * 128 + hg * 16 + (j >> 2)) * DM);
                uint4 v[20];
#pragma unroll
                for (int k = 0; k < 20; k++) v[k] = __ldg(src + (j & 3) + 4 * k);
                const float p0 = __uint_as_float(__shfl_sync(~0u, v[0].x, j & 28) << 16);
                float s[2] = {0.f, 0.f}, q[2] = {0.f, 0.f};
#pragma unroll
                for (int k = 0; k < 20; k++) {
                    const uint32_t w[4] = {v[k].x, v[k].y, v[k].z, v[k].w};
#pragma unroll
                    for (int i = 0; i < 4; i++) {
                        const float a = __uint_as_float(w[i] << 16) - p0, b = __uint_as_float(w[i] & 0xffff0000u) - p0;
                        s[0] += a; s[1] += b; q[0] = fmaf(a, a, q[0]); q[1] = fmaf(b, b, q[1]);
                    }
                }
                float s0 = s[0] + s[1], q0 = q[0] + q[1];
#pragma unroll
                for (int o = 1; o <= 2; o <<= 1) { s0 += __shfl_xor_sync(~0u, s0, o); q0 += __shfl_xor_sync(~0u, q0, o); }
                if ((j & 3) == 0) {
                    const float d = s0 * (1.0f / DM);
                    const uint32_t ms = pack2(p0 + d, sqrt_apx(rbf(rbf(fmaxf(fmaf(-d, d, q0 * (1.0f / DM)), 0.f)) + 1e-5f)));
                    asm volatile("st.global.cg.u64 [%0], %1;" ::"l"(g_rstat + mb * 128 + (j & 4) * 16 + hg * 8 + (j >> 3)), "l"(tagw(ms, tag)) : "memory");
                    g_piv[mb * 128 + hg * 16 + ((j >> 2) & 8) + (j & 4) + ((j >> 3) & 3)] = __ushort_as_bfloat16((unsigned short)ms);
                }
            }
            float o[4];
            int row;
            if (layer == 0) {
                ulonglong2 v;
#pragma unroll 1
                for (int it = 0; it < SPIN_MAX; it++) {
                    v = ld_tag2(reinterpret_cast<const ulonglong2*>(g_rstat + mb * 128) + j);
                    if (tag_ok(v, tag)) break;
                    __nanosleep(100);
                }
                o[0] = __uint_as_float((uint32_t)v.x << 16); o[1] = rcp_apx(__uint_as_float((uint32_t)v.x & 0xffff0000u));
                o[2] = __uint_as_float((uint32_t)v.y << 16); o[3] = rcp_apx(__uint_as_float((uint32_t)v.y & 0xffff0000u));
                row = 2 * j;
            } else {
                const int ch = j & 7, kg = (j >> 3) & 3;
                const unsigned char* src = stg + (j >> 5) * 8192 + (hg & 3) * 2048;
                float s[8], q[8], p0[8];
#pragma unroll
                for (int i = 0; i < 8; i++) { s[i] = 0.f; q[i] = 0.f; }
#pragma unroll 1
                for (int it = 0; it < 5; it++) {
                    uint4 v[4];
                    mbar_wait(bars + 8 * (it % A1_NST), it / A1_NST);
#pragma unroll
                    for (int k = 0; k < 4; k++) v[k] = *reinterpret_cast<const uint4*>(src + (it % A1_NST) * A1_STAGE + (4 * k + kg) * 128 + ((ch ^ ((4 * k + kg) & 7)) << 4));
                    if (it == 0) {
                        const uint4 pv = *reinterpret_cast<const uint4*>(src + (ch << 4));
                        const uint32_t w[4] = {pv.x, pv.y, pv.z, pv.w};
#pragma unroll
                        for (int i = 0; i < 4; i++) { p0[2 * i] = __uint_as_float(w[i] << 16); p0[2 * i + 1] = __uint_as_float(w[i] & 0xffff0000u); }
                    }
                    asm volatile("" :: "r"(v[0].x), "r"(v[1].x), "r"(v[2].x), "r"(v[3].x), "f"(p0[0]) : "memory");
                    __syncwarp();
                    if ((tid & 31) == 0) mbar_arrive(bar_rd + 8 * it);
#pragma unroll
                    for (int k = 0; k < 4; k++) {
                        const uint32_t w[4] = {v[k].x, v[k].y, v[k].z, v[k].w};
#pragma unroll
                        for (int i = 0; i < 4; i++) {
                            const float a = __uint_as_float(w[i] << 16) - p0[2 * i], b = __uint_as_float(w[i] & 0xffff0000u) - p0[2 * i + 1];
                            s[2 * i] += a; s[2 * i + 1] += b; q[2 * i] = fmaf(a, a, q[2 * i]); q[2 * i + 1] = fmaf(b, b, q[2 * i + 1]);
                        }
                    }
                }
#pragma unroll
                for (int i = 0; i < 4; i++) {
                    const bool up = kg & 2;
                    const float ss = __shfl_xor_sync(~0u, up ? s[i] : s[i + 4], 16), qq = __shfl_xor_sync(~0u, up ? q[i] : q[i + 4], 16);
                    s[i] = (up ? s[i + 4] : s[i]) + ss; q[i] = (up ? q[i + 4] : q[i]) + qq; p0[i] = up ? p0[i + 4] : p0[i];
                }
#pragma unroll
                for (int i = 0; i < 2; i++) {
                    const bool up = kg & 1;
                    const float ss = __shfl_xor_sync(~0u, up ? s[i] : s[i + 2], 8), qq = __shfl_xor_sync(~0u, up ? q[i] : q[i + 2], 8);
                    s[i] = (up ? s[i + 2] : s[i]) + ss; q[i] = (up ? q[i + 2] : q[i]) + qq; p0[i] = up ? p0[i + 2] : p0[i];
                }
                uint4* gp = g_halo + 86016 + mb * 512 + j;
                const float d0 = s[0] * (1.0f / 80.0f), d1 = s[1] * (1.0f / 80.0f);
                asm volatile("st.relaxed.gpu.global.v4.f32 [%0], {%1,%2,%3,%4};" ::"l"(gp + hg * 64), "f"(p0[0] + d0), "f"(fmaxf(fmaf(-d0, s[0], q[0]), 0.f)), "f"(p0[1] + d1), "f"(fmaxf(fmaf(-d1, s[1], q[1]), 0.f)) : "memory");
                __nanosleep(ST_SLEEP0);
                uint32_t pw[8][4], todo = 0xff;
#pragma unroll 1
                for (int it = 0; it < SPIN_MAX; it++) {
#pragma unroll
                    for (int k = 0; k < 8; k++)
                        if (todo >> k & 1) asm volatile("ld.relaxed.gpu.global.v4.u32 {%0,%1,%2,%3}, [%4];" : "=r"(pw[k][0]), "=r"(pw[k][1]), "=r"(pw[k][2]), "=r"(pw[k][3]) : "l"(gp + k * 64) : "memory");
#pragma unroll
                    for (int k = 0; k < 8; k++)
                        if (__all_sync(~0u, pw[k][0] != ~0u && pw[k][1] != ~0u && pw[k][2] != ~0u && pw[k][3] != ~0u)) todo &= ~(1u << k);
                    if (!todo) break;
                    __nanosleep(ST_SLEEP);
                }
#pragma unroll
                for (int r = 0; r < 2; r++) {
                    float mean = 0.f, m2 = 0.f;
#pragma unroll
                    for (int k = 0; k < 8; k++) mean += __uint_as_float(pw[k][2 * r]);
                    mean *= 0.125f;
#pragma unroll
                    for (int k = 0; k < 8; k++) {
                        const float dm = __uint_as_float(pw[k][2 * r]) - mean;
                        m2 += fmaf(80.0f * dm, dm, __uint_as_float(pw[k][2 * r + 1]));
                    }
                    o[2 * r] = rbf(mean);
                    o[2 * r + 1] = rcp_apx(rbf(sqrt_apx(rbf(rbf(m2 * (1.0f / DM)) + 1e-5f))));
                }
                row = (j >> 5) * 64 + (j & 7) * 8 + ((j >> 3) & 3) * 2;
                if (hg == 0) *reinterpret_cast<uint32_t*>(g_piv + SEQ + mb * 128 + 2 * (row & 60) + 4 * (row >> 6) + (row & 3)) = __byte_perm(__float_as_uint(o[0]), __float_as_uint(o[2]), 0x7632);
            }
#pragma unroll
            for (int r = 0; r < 2; r++)
                *reinterpret_cast<uint4*>(stg + A1_SM_XA + (row + r) * 16) = make_uint4(__byte_perm(__float_as_uint(-o[2 * r]), 0, 0x3232), __float_as_uint(-o[2 * r]) >> 16, 0u, 0u);
            *reinterpret_cast<float4*>(rst + row + (row >> 6) * 8) = make_float4(o[0], o[1], o[2], o[3]);
            fence_async_smem();
            TSTAMP1T(7, 320);
            if (tid == 320) DBGC(44);
            __syncwarp();
            if ((tid & 31) == 0) mbar_arrive(bar_stat);
        }
        if (tid == 320) DBGCAL(0);
        if (tid == 352) {
            mbar_wait(WO_LATE, 0);
            mbar_wait(bar_done, 0);
            bulk_load(sbase, wo + (hg * 8 + 6) * WOB, 2 * WOB, bar_wo);
            bulk_load(sbase + A1_SM_W0 + 2 * WOB, wo + (hg * 8 + 2) * WOB, WOB, bar_wo);
        }
        if (w < 10) {
            const int cw = w - 8;
            const uint32_t* fl = reinterpret_cast<const uint32_t*>(rsum + 2 * SEQ) + (((layer * 16 + mb) * 2 + cw) * 8 + (tid & 7)) * FSTR;
            const unsigned char* src = reinterpret_cast<const unsigned char*>(of) + mb * 163840 + cw * 10240 + (tid & 7) * 20480;
            const uint32_t sl = sbase + (cw ? A1_SM_A1 : A1_SM_A0);
            mbar_wait(cw ? bar_done : bar_kvf, 0);
            if ((tid & 31) == 0) {
                mbar_expect_tx(bar_f2 + 64 * cw + 64, 10240);
                tma_load_3d(sl + 51200, &tmR, layer ? 0 : hg * 80, layer ? hg * 80 : mb * 64, layer ? mb * 2 + cw : cw, bar_f2 + 64 * cw + 64);
            }
            __syncwarp();
            uint32_t pend = 0xffu & ~(1u << hg), v = 0;
            const uint32_t bo = wo_off((tid & 7) + ((tid & 7) < hg)) >> 4, lt = (1u << (tid & 31)) - 1;
#pragma unroll 1
            for (int it = 0; pend && it < 2 * SPIN_MAX; it++) {
                if (v != 4 && (pend >> (tid & 31) & 1)) asm volatile(A1_FLD " %0, [%1];" : "=r"(v) : "l"(fl) : "memory");
                uint32_t fr;
                asm volatile("{\n.reg .pred p;\nmbarrier.test_wait.parity.shared::cta.b64 p, [%1], 0;\nselp.b32 %0, 1, 0, p;\n}" : "=r"(fr) : "r"(bar_e2 + 16 * cw + (tid & 1) * 8) : "memory");
                fr = __ballot_sync(~0u, fr);
                uint32_t m = __ballot_sync(~0u, v == 4 || it >= A1_FSPIN) & pend;
                const int q = 8 - __popc(pend) + __popc(m & lt);
                m &= __ballot_sync(~0u, q < ((fr & 2) ? 8 : (fr & 1) ? 7 : 5));
                pend ^= m;
                if (m >> (tid & 31) & 1) DBGC(12 + cw * 8 + (tid & 7));
                if (!m) __nanosleep(A1_FSLEEP);
                else asm volatile("fence.proxy.async.global;" ::: "memory");
                if (m >> (tid & 31) & 1) {
                    bulk_load(q == 7 && !cw ? sbase + A1_SM_W0 : sl + (q < 6 ? q : q - 6) * 10240, src, 10240, bar_f2 + 64 * cw + 8 * q);
                    asm volatile("st.shared.u32 [%0], %1;" ::"r"(que + 32 * cw + 4 * q), "r"(bo) : "memory");
                    mbar_expect_tx(bar_f2 + 64 * cw + 8 * q, 10240);
                    DBGC(44 + cw * 8 + q);
                }
                __syncwarp();
            }
        }
    } else {
        if (tid == 0) {
            mbar_init(bar_stat, 3);
#pragma unroll
            for (int i = 0; i < 8; i++) mbar_init(bar_kv + 8 * i, 1);
            mbar_init(bars + 144, 1);
            mbar_init(bars + 160, 1);
#pragma unroll
            for (int i = 0; i < 5; i++) mbar_init(bar_rd + 8 * i, 2);
            asm volatile("fence.mbarrier_init.release.cluster;" ::: "memory");
        } else if (tid == 32) {
            mbar_init(bar_wo, 1); mbar_init(bar_done, 3); mbar_init(bar_pv, 4); mbar_init(bar_kvf, 8); mbar_init(bars + 240, 4);
#pragma unroll
            for (int i = 0; i < 4; i++) { mbar_init(bar_e2 + 8 * i, i == 1 ? 2 : 1); mbar_init(bars + 8 * (A1_NST + i), 2); }
            asm volatile("fence.mbarrier_init.release.cluster;" ::: "memory");
        } else if (tid == 64) {
#pragma unroll
            for (int i = 1; i <= 16; i++) mbar_init(bar_f2 + 8 * i, 1);
            asm volatile("fence.mbarrier_init.release.cluster;" ::: "memory");
        }
        asm volatile("bar.sync 0, 384;" ::: "memory");
        SPAN(1 + 4 * layer, 0);
        constexpr int on = 1;
        float acc[120];
        const int lane = tid & 31, warp = w & 7, g = lane >> 2, t = lane & 3;
        if (on) {
            SPAN(1 + 4 * layer, 1);
            TSTAMP1(0);
            if (threadIdx.x == 0) { GSTAMP(g_tim1, 15); }
            TSTAMP3(0);
            if (tid == 0) TSTAMP2(0);
            TSTAMP4(0);
            if (tid == 0) DBGC(60);
            if (layer == 0) a1_mainloop<0>(acc, sbase, bars, wg, tile); else a1_mainloop<1>(acc, sbase, bars, wg, tile);
            uint32_t ok;
            asm volatile("{\n.reg .pred p;\nmbarrier.test_wait.parity.shared::cta.b64 p, [%1], 0;\nselp.b32 %0, 1, 0, p;\n}" : "=r"(ok) : "r"(bar_stat) : "memory");
            if (tid == 128 && !ok) mbar_arrive(bars + 160);
            __syncwarp();
            mbar_wait(bar_stat, 0);
            wgmma_fence();
            wgmma_n240<0, 0>(acc, make_desc(sbase + A1_SM_XA + wg * 1024, 0, 128, 0), make_desc(sbase + A1_SM_XB, 0, 128, 0), 1);
            wgmma_commit();
            if (tid == 128 && ok) mbar_arrive(bars + 160);
            mbar_wait(bars + 8 * (A1_NST + 3), 1);
        }
        const float2* rw = rst + 16 * warp + 8 * wg;
        const float rb0 = rw[g + 8].y, ra = rw[g].y * 0.22360679774997896f, rb = rb0 * 0.22360679774997896f;
        wgmma_wait<0>();
        if ((tid & 127) == 0) mbar_arrive(bar_done);
        TSTAMP1(2);
        TSTAMP1T(13, 224);
        if ((tid & 127) == 0) DBGC(62 - wg);
        uint32_t f[2][30];
#pragma unroll
        for (int j = 10; j < 30; j++) f[1][j] = pack2(acc[4 * j + 2], acc[4 * j + 3]);
        if ((warp & 3) == 3) {
            uint4* hout = g_halo + (((layer * 16 + mb) * 8 + hg) * 2 + wg) * 168;
#pragma unroll
            for (int j = 0; j < 20; j += 4)
                asm volatile("st.relaxed.gpu.global.v4.u32 [%0], {%1,%2,%3,%4};" ::"l"(hout + 8 * j + lane), "r"(f[1][10 + j]), "r"(f[1][11 + j]), "r"(f[1][12 + j]), "r"(f[1][13 + j]) : "memory");
            if (t == 0) asm volatile("st.relaxed.gpu.global.f32 [%0], %1;" ::"l"(reinterpret_cast<float*>(hout + 160) + g), "f"(rb0) : "memory");
        }
        TSTAMP1T(12, 224);
        const uint32_t kvw = sbase + A1_SM_KV + (16 * warp + 8 * wg) * A1_KVP;
        const uint32_t mrow = kvw + (lane & 7) * A1_KVP + (lane >> 3) * 16;
#pragma unroll
        for (int j = 0; j < 20; j += 4) stsm_x4(mrow + 16 * A1_KVP + 16 * j, f[1][10 + j], f[1][11 + j], f[1][12 + j], f[1][13 + j]);
        __syncwarp();
        if (lane == 0 && (warp & 3) != 3) mbar_arrive(bar_kv + 8 * (warp + 1));
#pragma unroll
        for (int j = 0; j < 30; j++) f[0][j] = pack2(acc[4 * j], acc[4 * j + 1]);
        stsm_x4(mrow + 8 * A1_KVP + 160, f[0][20], f[0][21], f[0][22], f[0][23]);
        stsm_x4(mrow + 8 * A1_KVP + 224, f[0][24], f[0][25], f[0][26], f[0][27]);
        asm volatile("stmatrix.sync.aligned.m8n8.x2.shared.b16 [%0], {%1,%2};" ::"r"(mrow + 8 * A1_KVP + 288), "r"(f[0][28]), "r"(f[0][29]) : "memory");
#pragma unroll
        for (int j = 0; j < 10; j++) f[1][j] = pack2(acc[4 * j + 2], acc[4 * j + 3]);
        __syncwarp();
        uint32_t vb[10][2], vp[12], kp[12];
#pragma unroll
        for (int j = 0; j < 10; j += 2) ldsm_x4_t(&vb[j][0], kvw + (8 + (lane & 15)) * A1_KVP + 160 + (lane >> 4) * 16 + 16 * j);
        const bool up0 = 2 * t > g, up1 = 2 * t + 1 > g, edge = (mb | (warp & 3)) == 0;
        float rk[4];
        auto above = [&]() {
            mbar_wait(bar_kv + 8 * warp, 0);
#pragma unroll
            for (int j = 0; j < 12; j += 4) ldsm_x4(&kp[j], mrow + 16 * j);
            rk[0] = rw[2 * t - (up0 ? 8 : 0)].y; rk[1] = rw[2 * t + 1 - (up1 ? 8 : 0)].y;
#pragma unroll
            for (int j = 0; j < 12; j += 4) ldsm_x4_t(&vp[j], mrow + 160 + 16 * j - (j == 8 ? (lane & 16) * 2 : 0));
            __syncwarp();
            if (lane == 0) mbar_arrive(bar_kvf);
        };
        auto halo = [&]() {
            if (lane == 0) mbar_arrive(bar_kvf);
            const uint4* hin = g_halo + (((layer * 16 + mb - 1) * 8 + hg) * 2 + wg) * 168;
            uint32_t hv[22] = {};
            rk[0] = rw[2 * t].y; rk[1] = rw[2 * t + 1].y;
            if (mb > 0) {
#pragma unroll 1
                for (int it = 0; it < SPIN_MAX; it++) {
#pragma unroll
                    for (int k = 0; k < 20; k += 4)
                        asm volatile("ld.relaxed.gpu.global.v4.u32 {%0,%1,%2,%3}, [%4];" : "=r"(hv[k]), "=r"(hv[k + 1]), "=r"(hv[k + 2]), "=r"(hv[k + 3]) : "l"(hin + 8 * k + lane) : "memory");
                    asm volatile("ld.relaxed.gpu.global.v2.u32 {%0,%1}, [%2];" : "=r"(hv[20]), "=r"(hv[21]) : "l"(reinterpret_cast<const uint2*>(hin + 160) + t) : "memory");
                    uint32_t m = max(hv[20], hv[21]);
#pragma unroll
                    for (int k = 0; k < 20; k += 2) m = __vimax3_u32(m, hv[k], hv[k + 1]);
                    if (!__any_sync(~0u, m == ~0u)) break;
                }
            }
            if (tid == 0) mbar_arrive(bars + 144);
            if (lane == 0) DBGC(52 - 16 * wg);
#pragma unroll
            for (int j = 0; j < 10; j++) {
                kp[j] = hv[j];
                asm volatile("movmatrix.sync.aligned.m8n8.trans.b16 %0, %1;" : "=r"(vp[j]) : "r"(hv[10 + j]));
            }
            if (up0) rk[0] = __uint_as_float(hv[20]);
            if (up1) rk[1] = __uint_as_float(hv[21]);
        };
        rk[2] = rw[2 * t + (up0 ? 0 : 8)].y; rk[3] = rw[2 * t + 1 + (up1 ? 0 : 8)].y;
        uint32_t qs[4][2];
#pragma unroll
        for (int h = 0; h < 4; h++) {
            qs[h][0] = (t >> 1) == (h & 1) ? f[0][5 * (h >> 1) + 2] : 0u; qs[h][1] = (t >> 1) == (h & 1) ? f[1][5 * (h >> 1) + 2] : 0u;
            asm volatile("" : "+r"(qs[h][0]), "+r"(qs[h][1]));
        }
#pragma unroll
        for (int j = 0; j < 10; j++) asm volatile("" : "+r"(f[0][j]), "+r"(f[1][j]), "+r"(f[0][10 + j]));
        if (warp & 3) above(); else if (wg) halo();
        TSTAMP1T(10, 64);
        float sc[4][3][4];
#pragma unroll
        for (int h = 0; h < 4; h++) {
            const int jb = 5 * (h >> 1) + 3 * (h & 1), js = 5 * (h >> 1) + 2;
#pragma unroll
            for (int nt = 1; nt < 3; nt++) {
#pragma unroll
                for (int e = 0; e < 4; e++) sc[h][nt][e] = 0.f;
                mma_bf16(sc[h][nt], f[0][jb], f[1][jb], f[0][jb + 1], f[1][jb + 1], f[nt - 1][10 + jb], f[nt - 1][11 + jb]);
                mma_bf16_k8(sc[h][nt], qs[h][0], qs[h][1], f[nt - 1][10 + js]);
            }
        }
        if (tid == 128) mbar_arrive(bars + 240);
        if (warp == 0) halo();
        TSTAMP1(8);
#pragma unroll
        for (int h = 0; h < 4; h++) {
            const int jb = 5 * (h >> 1) + 3 * (h & 1), js = 5 * (h >> 1) + 2;
#pragma unroll
            for (int e = 0; e < 4; e++) sc[h][0][e] = 0.f;
            mma_bf16(sc[h][0], f[0][jb], f[1][jb], f[0][jb + 1], f[1][jb + 1], kp[jb], kp[jb + 1]);
            mma_bf16_k8(sc[h][0], qs[h][0], qs[h][1], kp[js]);
        }
        if (warp > 4) { __syncwarp(); if (lane == 0) mbar_arrive(bars + 240); }
        TSTAMP1T(3, 64);
        float p[4][4], sum[4][2];
        uint32_t lg[4][2], mx[4];
        const float rl[4] = {rk[0] * ra, rk[1] * ra, rk[2] * rb, rk[3] * rb};
        auto max2 = [](uint32_t a, uint32_t b) { uint32_t r; asm("max.bf16x2 %0, %1, %2;" : "=r"(r) : "r"(a), "r"(b)); return r; };
#pragma unroll
        for (int h = 0; h < 4; h++) {
            lg[h][0] = pack2((up0 ? sc[h][0][0] : sc[h][1][0]) * rl[0], (up0 ? sc[h][1][2] : sc[h][2][2]) * rl[2]);
            lg[h][1] = pack2((up1 ? sc[h][0][1] : sc[h][1][1]) * rl[1], (up1 ? sc[h][1][3] : sc[h][2][3]) * rl[3]);
            if (edge) {
                if (up0) lg[h][0] = __byte_perm(lg[h][0], 0xce6eu, 0x3254);
                if (up1) lg[h][1] = __byte_perm(lg[h][1], 0xce6eu, 0x3254);
            }
            mx[h] = max2(lg[h][0], lg[h][1]);
        }
#pragma unroll
        for (int o = 1; o <= 2; o <<= 1)
#pragma unroll
            for (int h = 0; h < 4; h++) mx[h] = max2(mx[h], __shfl_xor_sync(~0u, mx[h], o));
#pragma unroll
        for (int h = 0; h < 4; h++)
#pragma unroll
            for (int r = 0; r < 2; r++) {
                const float m = __uint_as_float(r ? mx[h] & 0xffff0000u : mx[h] << 16);
#pragma unroll
                for (int e = 0; e < 2; e++)
                    asm("ex2.approx.ftz.f32 %0, %1;" : "=f"(p[h][2 * r + e]) : "f"((__uint_as_float(r ? lg[h][e] & 0xffff0000u : lg[h][e] << 16) - m) * 1.4426950408889634f));
                sum[h][r] = p[h][2 * r] + p[h][2 * r + 1];
            }
#pragma unroll
        for (int o = 1; o <= 2; o <<= 1)
#pragma unroll
            for (int h = 0; h < 4; h++)
#pragma unroll
                for (int r = 0; r < 2; r++) sum[h][r] += __shfl_xor_sync(~0u, sum[h][r], o);
        TSTAMP1T(5, 64);
        const uint32_t mu = (up0 ? 0xffffu : 0u) | (up1 ? 0xffff0000u : 0u);
        uint32_t ob[10][2];
#pragma unroll
        for (int P = 0; P < 2; P++) {
            float os[2][4];
#pragma unroll
            for (int e = 0; e < 2; e++) {
                const int h = 2 * P + e;
                const float i0 = rcp_apx(sum[h][0]), i1 = rcp_apx(sum[h][1]);
                const uint32_t w0 = pack2(p[h][0] * rk[0] * i0, p[h][1] * rk[1] * i0), w1 = pack2(p[h][2] * rk[2] * i1, p[h][3] * rk[3] * i1);
#pragma unroll
                for (int dt = 0; dt < 3; dt++) {
                    const int j = 5 * P + (dt < 2 ? 3 * e + dt : 2);
                    float o[4] = {0.f, 0.f, 0.f, 0.f};
                    mma_bf16(o, w0 & ~mu, w1 & mu, 0u, w1 & ~mu, vb[j][0], vb[j][1]);
                    mma_bf16_k8(o, w0 & mu, 0u, vp[j]);
                    if (dt < 2) { ob[j][0] = pack2(o[0], o[1]); ob[j][1] = pack2(o[2], o[3]); }
                    else { os[e][0] = o[0]; os[e][1] = o[1]; os[e][2] = o[2]; os[e][3] = o[3]; }
                }
            }
#pragma unroll
            for (int k = 0; k < 4; k++) os[0][k] = t < 2 ? os[0][k] : os[1][k];
            ob[5 * P + 2][0] = pack2(os[0][0], os[0][1]); ob[5 * P + 2][1] = pack2(os[0][2], os[0][3]);
        }
        const uint32_t sl = sbase + (wg ? A1_SM_A1 : A1_SM_A0);
        const uint32_t o0 = (warp & 3) * 2048 + g * 64 + ((t ^ (g >> 1)) << 4), o1 = 8192 + (warp & 3) * 512 + g * 32 + ((t ^ ((g >> 2) << 1)) << 3);
        mbar_wait(bar_done, 0);
        if (wg == 0) mbar_wait(bar_kvf, 0);
#pragma unroll
        for (int h = 0; h < 2; h++) {
            asm volatile("st.shared.v4.u32 [%0], {%1,%2,%3,%4};" ::"r"(sl + o0 + h * 1024), "r"(ob[0][h]), "r"(ob[1][h]), "r"(ob[2][h]), "r"(ob[3][h]) : "memory");
            asm volatile("st.shared.v4.u32 [%0], {%1,%2,%3,%4};" ::"r"(sl + o0 + h * 1024 + 512), "r"(ob[4][h]), "r"(ob[5][h]), "r"(ob[6][h]), "r"(ob[7][h]) : "memory");
            asm volatile("st.shared.v2.u32 [%0], {%1,%2};" ::"r"(sl + o1 + h * 256), "r"(ob[8][h]), "r"(ob[9][h]) : "memory");
        }
        fence_async_smem();
        __syncwarp();
        TSTAMP1T(4, 64);
        TSTAMP1(1);
        TSTAMP2(1);
        const unsigned char* ot = reinterpret_cast<const unsigned char*>(of) + mb * 163840 + wg * 10240;
        if (lane == 0) {
            asm volatile("cp.async.bulk.global.shared::cta.bulk_group [%0], [%1], 2048;" ::"l"(ot + hg * 20480 + (warp & 3) * 2048), "r"(sl + (warp & 3) * 2048) : "memory");
            asm volatile("cp.async.bulk.global.shared::cta.bulk_group [%0], [%1], 512;" ::"l"(ot + hg * 20480 + 8192 + (warp & 3) * 512), "r"(sl + 8192 + (warp & 3) * 512) : "memory");
            asm volatile("cp.async.bulk.commit_group;" ::: "memory");
            if (wg == 0) mbar_arrive(bar_pv);
            asm volatile("cp.async.bulk.wait_group 0;" ::: "memory");
            asm volatile(A1_FRED " [%0], 1;" ::"l"(reinterpret_cast<uint32_t*>(rsum + 2 * SEQ) + (((layer * 16 + mb) * 2 + wg) * 8 + hg) * FSTR) : "memory");
            DBGC(4 + warp);
        }
        TSTAMP4(11);
        float ac2[40];
        const uint64_t db0 = make_desc(sbase, 1024, 256, 3), db1 = make_desc(sbase + 10240, 512, 256, 3), da0 = make_desc(sl, 16, 1024, 2), da1 = make_desc(sl + 8192, 16, 256, 3);
        const uint32_t o7 = wg ? 640 : (A1_SM_W0 - A1_SM_A0) >> 4;
        const uint32_t trow = ((lane & 7) + 8 * (lane >> 4)) * 128 + (((2 * (warp & 3) + ((lane >> 3) & 1)) ^ (lane & 7)) << 4);
        uint32_t xr[10][2];
        mbar_wait(bar_f2 + 64 * wg + 64, 0);
        if (layer == 0) {
#pragma unroll
            for (int j = 0; j < 10; j += 2) ldsm_x4(&xr[j][0], sl + 51200 + (16 * (warp & 3) + (lane & 15)) * 160 + (lane >> 4) * 16 + 16 * j);
        } else {
#pragma unroll
            for (int j = 0; j < 10; j += 2) ldsm_x4_t(&xr[j][0], sl + 51200 + trow + 1024 * j);
        }
        const uint32_t ri = __shfl_sync(~0u, layer * SEQ + (wg * 2 + ((g >> 1) & 1)) * 512 + (mb * 16 + 4 * (warp & 3) + (g >> 2)) * 2 + (g & 1), lane);
        mbar_wait(bar_wo, 0);
        if (wg) mbar_wait(bar_pv, 0);
        if (wg) asm volatile("bar.sync 2, 128;" ::: "memory"); else asm volatile("bar.sync 1, 128;" ::: "memory");
        TSTAMP2(2);
#pragma unroll
        for (int q = 0; q < 8; q++) {
            uint32_t bo = wo_off(0) >> 4;
            if (q) {
                mbar_wait(bar_f2 + 64 * wg + 8 * q, 0);
                asm volatile("ld.shared.u32 %0, [%1];" : "=r"(bo) : "r"(que + 32 * wg + 4 * q) : "memory");
                bo = __shfl_sync(~0u, bo, 0);
                TSTAMP4(q);
                if (q == 1 && (tid & 127) == 0) DBGC(29 + 8 * wg);
            }
            wgmma_fence();
#pragma unroll
            for (int j = 0; j < 5; j++) wgmma_n80(ac2, (j < 4 ? da0 : da1) + (q == 7 ? o7 : 0u) + (uint64_t)((q < 6 ? q * 640 : 0) + (j & 2) * 16 + (j & 1) * 2), (j < 4 ? db0 : db1) + bo + (uint64_t)((j & 2) * 160 + (j & 1) * 32), j || q);
            wgmma_commit();
            if (q == 0) {
                wgmma_wait<0>();
                if ((tid & 127) == 0) { mbar_arrive(bar_e2 + 16 * wg); mbar_arrive(bar_e2 + 8); }
            }
            if (q == 2 && wg) {
                wgmma_wait<1>();
                if (tid == 128) mbar_arrive(bar_e2 + 24);
            }
        }
        if ((tid & 127) == 0) DBGC(28 + wg * 8 + 7);
        TSTAMP2(3);
        wgmma_wait<0>();
        TSTAMP2(4);
        if (__any_sync(~0u, ac2[0] != ac2[0] || ac2[2] != ac2[2])) {
#pragma unroll
            for (int i = 0; i < 40; i++) ac2[i] = 0.f;
            uint32_t a[20], an[20];
            auto lda = [&](uint32_t (&r)[20], int h) {
#pragma unroll
                for (int u = 0; u < 4; u++)
                    asm volatile("ld.relaxed.gpu.global.v4.u32 {%0,%1,%2,%3}, [%4];" : "=r"(r[4 * u]), "=r"(r[4 * u + 1]), "=r"(r[4 * u + 2]), "=r"(r[4 * u + 3]) : "l"(ot + h * 20480 + o0 + u * 512) : "memory");
#pragma unroll
                for (int u = 0; u < 2; u++)
                    asm volatile("ld.relaxed.gpu.global.v2.u32 {%0,%1}, [%2];" : "=r"(r[16 + 2 * u]), "=r"(r[17 + 2 * u]) : "l"(ot + h * 20480 + o1 + u * 256) : "memory");
            };
            lda(an, 0);
#pragma unroll 5
            for (int k = lane; k < WOB / 16; k += 32)
                reinterpret_cast<uint4*>(stg + (sl - sbase))[k] = __ldcg(reinterpret_cast<const uint4*>(wo + hg * 8 * WOB) + k);
            __syncwarp();
#pragma unroll 1
            for (int h = 0; h < 8; h++) {
#pragma unroll 1
                for (int it = 0; it < SPIN_MAX; it++) {
                    uint32_t m = 0;
#pragma unroll
                    for (int k = 0; k < 20; k += 2) m = __vimax3_u32(m, an[k], an[k + 1]);
                    if (!__any_sync(~0u, m == ~0u)) break;
                    lda(an, h);
                }
#pragma unroll
                for (int k = 0; k < 20; k++) a[k] = an[k];
                lda(an, min(h + 1, 7));
                const uint32_t bp = h == hg ? sl : sbase + wo_off(h + (h < hg));
                const int r0 = 8 * ((lane & 7) >> 1) + 2 * (lane >> 3) + (lane & 1), r2 = 4 * ((lane & 7) >> 1) + 2 * ((lane >> 3) & 1) + (lane & 1);
#pragma unroll
                for (int n = 0; n < 10; n++) {
                    uint32_t b[12];
                    ldsm_x4_t(b, bp + (n >> 1) * 1024 + r0 * 32 + (((n ^ (r0 >> 2)) & 1) << 4));
                    ldsm_x4_t(b + 4, bp + 5120 + (n >> 1) * 1024 + r0 * 32 + (((n ^ (r0 >> 2)) & 1) << 4));
                    ldsm_x4_t(b + 8, bp + 10240 + (n >> 1) * 512 + r2 * 32 + (((n ^ (r2 >> 2)) & 1) << 4));
                    mma_bf16(ac2 + 4 * n, a[0], a[8], a[1], a[9], b[0], b[1]); mma_bf16(ac2 + 4 * n, a[2], a[10], a[3], a[11], b[2], b[3]);
                    mma_bf16(ac2 + 4 * n, a[4], a[12], a[5], a[13], b[4], b[5]); mma_bf16(ac2 + 4 * n, a[6], a[14], a[7], a[15], b[6], b[7]);
                    mma_bf16(ac2 + 4 * n, a[16], a[18], a[17], a[19], b[8], b[9]);
                }
            }
        }
#pragma unroll
        for (int j = 0; j < 10; j++)
#pragma unroll
            for (int hh = 0; hh < 2; hh++) {
                const uint32_t a = pack2(ac2[4 * j + 2 * hh], ac2[4 * j + 2 * hh + 1]);
                const __nv_bfloat162 r = __hadd2_rn(*reinterpret_cast<const __nv_bfloat162*>(&xr[j][hh]), *reinterpret_cast<const __nv_bfloat162*>(&a));
                xr[j][hh] = *reinterpret_cast<const uint32_t*>(&r);
            }
        const uint32_t so = sl + 30720;
#pragma unroll
        for (int j = 0; j < 10; j += 2) stsm_x4_t(so + trow + 1024 * j, xr[j][0], xr[j][1], xr[j + 1][0], xr[j + 1][1]);
        fence_async_smem();
        if (wg) asm volatile("bar.sync 2, 128;" ::: "memory"); else asm volatile("bar.sync 1, 128;" ::: "memory");
        TSTAMP2(5);
        if ((tid & 127) == 0) {
            asm volatile("cp.async.bulk.tensor.2d.global.shared::cta.bulk_group [%0, {%1, %2}], [%3];" ::"l"(&tmX1), "r"(mb * 128 + 64 * wg), "r"(hg * 80), "r"(so) : "memory");
            asm volatile("cp.async.bulk.commit_group;" ::: "memory");
        }
        __syncwarp();
        const float p0 = *(volatile const float*)&rw[g].x, p1 = *(volatile const float*)&rw[g + 8].x;
        float s[3][4] = {};
        const uint32_t pp[2] = {__byte_perm(__float_as_uint(p0), 0, 0x3232), __byte_perm(__float_as_uint(p1), 0, 0x3232)};
#pragma unroll
        for (int j = 0; j < 10; j += 2) {
            const uint32_t d0 = sub2(xr[j][0], pp[0]), d1 = sub2(xr[j][1], pp[1]), d2 = sub2(xr[j + 1][0], pp[0]), d3 = sub2(xr[j + 1][1], pp[1]);
            mma_bf16(s[0], xr[j][0], xr[j][1], xr[j + 1][0], xr[j + 1][1], 0x3f803f80u, 0x3f803f80u);
            mma_bf16(s[1], d0, d1, d2, d3, d0, d2);
            mma_bf16(s[2], d0, d1, d2, d3, d1, d3);
        }
        if (t == (g >> 1)) {
            float2* rp = rsum + ri;
            asm volatile("red.relaxed.gpu.global.add.v2.f32 [%0], {%1, %2};" ::"l"(rp), "f"(fmaf(-80.f, p0, s[0][0])), "f"((g & 1) ? s[1][1] : s[1][0]) : "memory");
            asm volatile("red.relaxed.gpu.global.add.v2.f32 [%0], {%1, %2};" ::"l"(rp + 4), "f"(fmaf(-80.f, p1, s[0][2])), "f"((g & 1) ? s[2][3] : s[2][2]) : "memory");
        }
        asm volatile("cp.async.bulk.wait_group.read 0;" ::: "memory");
        TSTAMP2(6);
        if (tid == 0) DBGC(63);
        if (tid == 128) DBGC(28);
        if (tid == 0) DBGCAL(2);
        GSTAMP(g_tim1, 14);
        SPAN(1 + 4 * layer, 3);
    }
}

static int h_nsm;
static void* h_sym[11];
static TileTab h_tab;
static CUtensorMap h_tmX0, h_tmX1, h_tmR0, h_tmR1, h_tmX1st, h_tmOut, h_tmWq, h_tmWo, h_tmWt;
typedef CUresult (*PFN_encodeTiled)(CUtensorMap*, CUtensorMapDataType, cuuint32_t, void*, const cuuint64_t*, const cuuint64_t*,
                                    const cuuint32_t*, const cuuint32_t*, CUtensorMapInterleave, CUtensorMapSwizzle,
                                    CUtensorMapL2promotion, CUtensorMapFloatOOBfill);
static void make_tmap(CUtensorMap* tm, const void* ptr, uint64_t cols, uint64_t rows, uint32_t bc, uint32_t br, CUtensorMapSwizzle sw, uint64_t pitch = 0, uint64_t hi = 0, uint32_t bh = 2) {
    static PFN_encodeTiled fn = nullptr;
    if (!fn) {
        void* p = nullptr; cudaDriverEntryPointQueryResult qr;
        cudaGetDriverEntryPoint("cuTensorMapEncodeTiled", &p, cudaEnableDefault, &qr);
        fn = (PFN_encodeTiled)p;
    }
    if (br == 0) {
        cuuint64_t dims[5] = {16, 2, rows / 8, 4, cols / 16}; cuuint64_t strides[4] = {cols * 2, cols * 16, cols * 4, 32};
        cuuint32_t box[5] = {16, 2, bc, 4, 5}; cuuint32_t es[5] = {1, 1, 1, 1, 1};
        fn(tm, CU_TENSOR_MAP_DATA_TYPE_BFLOAT16, 5, const_cast<void*>(ptr), dims, strides, box, es, CU_TENSOR_MAP_INTERLEAVE_NONE, sw,
           CU_TENSOR_MAP_L2_PROMOTION_L2_128B, CU_TENSOR_MAP_FLOAT_OOB_FILL_NONE);
        return;
    }
    if (bh == 0) {
        cuuint64_t dims[5] = {64, 64, 2, 16, 10}; cuuint64_t strides[4] = {pitch * 2, hi * 2, cols * 2, rows * 2};
        cuuint32_t box[5] = {64, 64, 2, 1, 1}; cuuint32_t es[5] = {1, 1, 1, 1, 1};
        fn(tm, CU_TENSOR_MAP_DATA_TYPE_BFLOAT16, 5, const_cast<void*>(ptr), dims, strides, box, es, CU_TENSOR_MAP_INTERLEAVE_NONE, sw,
           CU_TENSOR_MAP_L2_PROMOTION_L2_128B, CU_TENSOR_MAP_FLOAT_OOB_FILL_NONE);
        return;
    }
    if (hi) {
        cuuint64_t dims[3] = {cols, rows, hi == 64 ? 32u : hi == 16 ? 120u : 2u}; cuuint64_t strides[2] = {pitch * 2, hi * 2};
        cuuint32_t box[3] = {bc, br, bh}; cuuint32_t es[3] = {1, 1, 1};
        fn(tm, CU_TENSOR_MAP_DATA_TYPE_BFLOAT16, 3, const_cast<void*>(ptr), dims, strides, box, es, CU_TENSOR_MAP_INTERLEAVE_NONE, sw,
           CU_TENSOR_MAP_L2_PROMOTION_L2_128B, CU_TENSOR_MAP_FLOAT_OOB_FILL_NONE);
        return;
    }
    cuuint64_t dims[2] = {cols, rows}; cuuint64_t strides[1] = {(pitch ? pitch : cols) * 2};
    cuuint32_t box[2] = {bc, br}; cuuint32_t es[2] = {1, 1};
    fn(tm, CU_TENSOR_MAP_DATA_TYPE_BFLOAT16, 2, const_cast<void*>(ptr), dims, strides, box, es, CU_TENSOR_MAP_INTERLEAVE_NONE, sw,
       CU_TENSOR_MAP_L2_PROMOTION_L2_128B, CU_TENSOR_MAP_FLOAT_OOB_FILL_NONE);
}
template <typename... Args>
static void launch_pdl(void (*kern)(Args...), int grid, int block, int smem, Args... args) {
    cudaLaunchConfig_t cfg = {};
    cfg.gridDim = dim3(grid); cfg.blockDim = dim3(block); cfg.dynamicSmemBytes = smem; cfg.stream = cudaStreamPerThread;
    cudaLaunchAttribute at[1];
    at[0].id = cudaLaunchAttributeProgrammaticStreamSerialization; at[0].val.programmaticStreamSerializationAllowed = 1;
    cfg.attrs = at; cfg.numAttrs = 1;
    cudaLaunchKernelEx(&cfg, kern, args...);
}
static void launch_stage(int k, void* const* d_in, void* d_out) {
    const KgIn kg = {(const bf16*)d_in[4], (const bf16*)d_in[5], (const bf16*)d_in[6], (const bf16*)d_in[7], (const bf16*)d_in[8], (const bf16*)d_in[9], (const bf16*)d_in[0], (const bf16*)d_in[1], (const bf16*)d_in[2],
                      (uint4*)h_sym[0], (uint4*)h_sym[1], (uint4*)h_sym[2], (uint4*)h_sym[3], (uint4*)h_sym[4], (float*)h_sym[5]};
    switch (k) {
        case 0: kgen_kernel<<<128, 512, KG_SMEM, cudaStreamPerThread>>>(kg, h_tmWq, h_tmWo, h_tmWt); break;
        case 1: launch_pdl(a1_kernel, h_nsm, A1_THREADS, A1_SMEM, 0, (const bf16*)d_in[0], (const unsigned char*)h_sym[1], (const unsigned char*)h_sym[2], (float2*)h_sym[4], (uint4*)h_sym[6], h_tmX0, h_tmR0, h_tmX1st, h_tab); break;
        case 3: launch_pdl(conv_kernel, DM / CV_CPB, CV_THREADS, CV_SMEM, 0, (const uint4*)h_sym[7], (const float4*)h_sym[4], (const bf16*)h_sym[8], (bf16*)h_sym[9], (const uint4*)h_sym[0], h_tmOut); break;
        case 5: launch_pdl(a1_kernel, h_nsm, A1_THREADS, A1_SMEM, 1, (const bf16*)d_in[0], (const unsigned char*)h_sym[1], (const unsigned char*)h_sym[2], (float2*)h_sym[4], (uint4*)h_sym[6], h_tmX1, h_tmR1, h_tmX1st, h_tab); break;
        case 7: launch_pdl(conv_kernel, DM / CV_CPB, CV_THREADS, CV_SMEM, 1, (const uint4*)h_sym[7] + SEQ / 8, (const float4*)h_sym[4] + SEQ / 2, (const bf16*)h_sym[8], (bf16*)h_sym[10], (const uint4*)h_sym[0], h_tmOut); break;
        default: break;
    }
}
static int n_stage_kernels() { return 9; }
static const char* stage_name(int k) { const char* n[] = {"kgen", "a1", "a2", "conv", "tr", "a1", "a2", "conv", "tr"}; return n[k]; }

extern "C" void kernel_launch(void* const* d_in, const int* in_sizes, int n_in, void* d_out, int out_size) {
    (void)in_sizes; (void)n_in; (void)out_size;
    static const void *p_in = nullptr, *p_w1 = nullptr, *p_w2 = nullptr, *p_out = nullptr;
    if (p_in != d_in[0] || p_w1 != d_in[1] || p_w2 != d_in[2] || p_out != d_out) {
        cudaFuncSetAttribute(conv_kernel, cudaFuncAttributeMaxDynamicSharedMemorySize, CV_SMEM);
        cudaFuncSetAttribute(kgen_kernel, cudaFuncAttributeMaxDynamicSharedMemorySize, KG_SMEM);
        cudaFuncSetAttribute(a1_kernel, cudaFuncAttributeMaxDynamicSharedMemorySize, A1_SMEM);
        int dev; cudaGetDevice(&dev); cudaDeviceGetAttribute(&h_nsm, cudaDevAttrMultiProcessorCount, dev);
        if (h_nsm != 132) h_nsm = 128;
        h_tab.ns = h_nsm == 132 ? 132 : ~0u;
        for (int i = 0; i < 264; i++) {
            const int h = (i - 64) >> 1;
            const int t = i >= 132 ? i - 132 : i < 64 ? ((i >> 1) & 7) * 16 + (i >> 4) * 2 + (i & 1) : i < 120 ? (1 + h % 7) * 16 + 8 + (h / 7) * 2 + (i & 1) : i < 124 ? 128 : i - 116;
            const int hg = (4 * (t >> 6) + (t & 3)) & 7;
            h_tab.e[i] = {(unsigned char)((t >> 2) & 15), (unsigned char)hg, (unsigned char)(5 * (hg >> 2)), (unsigned char)t, (uint32_t)(hg * 10 * WQ_STAGE)};
        }
        cudaGetSymbolAddress(&h_sym[0], g_tap); cudaGetSymbolAddress(&h_sym[1], g_wq); cudaGetSymbolAddress(&h_sym[2], g_wo);
        cudaGetSymbolAddress(&h_sym[3], g_halo); cudaGetSymbolAddress(&h_sym[4], g_sum); cudaGetSymbolAddress(&h_sym[5], g_csp); cudaGetSymbolAddress(&h_sym[6], g_of);
        cudaGetSymbolAddress(&h_sym[7], g_piv); cudaGetSymbolAddress(&h_sym[8], g_x1T); cudaGetSymbolAddress(&h_sym[9], g_xcT); cudaGetSymbolAddress(&h_sym[10], g_yT);
        void *px1, *px2;
        cudaGetSymbolAddress(&px1, g_x1T); cudaGetSymbolAddress(&px2, g_xcT);
        make_tmap(&h_tmX0, d_in[0], 128 * 640, 64, 64, 64, CU_TENSOR_MAP_SWIZZLE_128B, 1280, 640, 0);
        make_tmap(&h_tmX1, px2, 128, 64 * XCP, 64, 64, CU_TENSOR_MAP_SWIZZLE_128B, XCP, 64, 0);
        make_tmap(&h_tmR0, d_in[0], 640, 1024, 80, 64, CU_TENSOR_MAP_SWIZZLE_NONE, 1280, 640, 1);
        make_tmap(&h_tmR1, px2, 64, 640, 64, 80, CU_TENSOR_MAP_SWIZZLE_128B, XCP, 64, 1);
        make_tmap(&h_tmX1st, px1, 2048, 640, 64, 80, CU_TENSOR_MAP_SWIZZLE_128B, XCP);
        make_tmap(&h_tmWq, d_in[1], 16, 640, 16, 32, CU_TENSOR_MAP_SWIZZLE_32B, 1920, 16, 5);
        make_tmap(&h_tmWo, d_in[2], 640, 640, 4, 0, CU_TENSOR_MAP_SWIZZLE_32B);
        make_tmap(&h_tmWt, d_in[2], 640, 640, 2, 0, CU_TENSOR_MAP_SWIZZLE_32B);
        make_tmap(&h_tmOut, d_out, 640, 1024, 80, 8, CU_TENSOR_MAP_SWIZZLE_NONE, 1280, 640, 1);
        p_in = d_in[0]; p_w1 = d_in[1]; p_w2 = d_in[2]; p_out = d_out;
    }
    for (int k = 0; k < n_stage_kernels(); k++) launch_stage(k, d_in, d_out);
}
```

```cpp
#include <cuda_runtime.h>
#include <cuda_bf16.h>
#include <stdint.h>
#include <cuda.h>

typedef __nv_bfloat16 bf16;

constexpr int SEQ = 2048;
constexpr int DM = 640;
constexpr int NMODE = 192;

__device__ __forceinline__ float bf2f(bf16 v) { return __bfloat162float(v); }
__device__ __forceinline__ float rbf(float v) {
    uint32_t r;
    asm("cvt.rn.bf16x2.f32 %0, %1, %2;" : "=r"(r) : "f"(v), "f"(0.f));
    return __uint_as_float(r);
}
__device__ __forceinline__ uint32_t pack2(float lo, float hi) {
    __nv_bfloat162 t = __floats2bfloat162_rn(lo, hi);
    return *reinterpret_cast<uint32_t*>(&t);
}
__device__ __forceinline__ void pdl_sync() {
    asm volatile("griddepcontrol.wait;" ::: "memory");
    asm volatile("griddepcontrol.launch_dependents;" ::: "memory");
}
__device__ __forceinline__ float sqrt_apx(float v) { float r; asm("sqrt.approx.ftz.f32 %0, %1;" : "=f"(r) : "f"(v)); return r; }
__device__ __forceinline__ float rcp_apx(float v) { float r; asm("rcp.approx.ftz.f32 %0, %1;" : "=f"(r) : "f"(v)); return r; }
__device__ __forceinline__ uint32_t smem_u32(const void* p) { return (uint32_t)__cvta_generic_to_shared(p); }

constexpr int TAPB = 2 * 152 * 8;
__device__ __align__(128) uint4 g_tap[DM * 128];
#define XPAD 64
constexpr int XCP = SEQ + XPAD;
__device__ __align__(128) bf16 g_x1T[DM * XCP];
__device__ __align__(128) bf16 g_xcT[DM * XCP];
__device__ __align__(128) uint4 g_of[128 * 1280];
constexpr int WQ_STAGE = 240 * 128, WOB = 80 * 160;
__device__ __align__(128) uint4 g_wq[8 * 10 * WQ_STAGE / 16];
__device__ __align__(128) uint4 g_wo[64 * WOB / 16];
__device__ __align__(16) float g_csp[10 * 1920];
#define FSTR 32
__device__ __align__(128) float2 g_sum[2 * SEQ + 256 * FSTR];
__device__ __align__(16) bf16 g_piv[2 * SEQ];
__device__ __align__(128) bf16 g_yT[DM * XCP];
__device__ uint32_t g_epoch;
__device__ __align__(16) unsigned long long g_rstat[SEQ];
__device__ __align__(128) uint4 g_halo[640 * 148];
__device__ __forceinline__ unsigned long long tagw(uint32_t payload, uint32_t tag) { return ((unsigned long long)tag << 32) | payload; }
__device__ __forceinline__ ulonglong2 ld_tag2(const ulonglong2* p) {
    ulonglong2 v;
    asm volatile("ld.relaxed.gpu.global.v2.u64 {%0, %1}, [%2];" : "=l"(v.x), "=l"(v.y) : "l"(p) : "memory");
    return v;
}
__device__ __forceinline__ bool tag_ok(ulonglong2 v, uint32_t tag) { return (uint32_t)(v.x >> 32) == tag && (uint32_t)(v.y >> 32) == tag; }
__device__ __forceinline__ uint32_t ld_epoch() { uint32_t v; asm volatile("ld.relaxed.gpu.global.u32 %0, [%1];" : "=r"(v) : "l"(&g_epoch) : "memory"); return v + 1; }
constexpr int SPIN_MAX = 1 << 20;
__device__ uint32_t g_started[4];
__device__ __forceinline__ void sm_started(int slot) { asm volatile("red.relaxed.gpu.global.add.u32 [%0], 1;" ::"l"(g_started + slot) : "memory"); }
__device__ __noinline__ void sm_idle(int slot) {
    if (threadIdx.x) return;
    sm_started(slot);
    const uint32_t want = ld_epoch() * gridDim.x;
    pdl_sync();
#pragma unroll 1
    for (int it = 0; it < SPIN_MAX; it++) {
        uint32_t v;
        asm volatile("ld.relaxed.gpu.global.u32 %0, [%1];" : "=r"(v) : "l"(g_started + slot) : "memory");
        if ((int)(v - want) >= 0) break;
        __nanosleep(100);
    }
}
struct TileTab { uint32_t ns, pad; struct { unsigned char mb, hg, kb0, tile; uint32_t woff; } __align__(8) e[264]; };
__device__ __forceinline__ bool elect() {
    uint32_t p;
    asm volatile("{\n.reg .pred p;\nelect.sync _|p, 0xffffffff;\nselp.b32 %0, 1, 0, p;\n}" : "=r"(p));
    return p;
}
#define DBG_SYMS
#define TSTAMP(i)
#define TSTAMP1(i)
#define TSTAMP1T(i, t)
#define TSTAMP1X(i, t)
#define SPAN(k, i)
#define GSTAMP(arr, i)
#define TSTAMP2(i)
#define TSTAMP3(i)
#define TSTAMP4(i)
#define TSTAMPK(i, t)
#define TSTAMPC(i)
#define DBGC(i)
#define DBGV(i, v)
#define DBGCAL(i)

#define CST(i)
#define CST_END
#define CST_EXTRA 0
__device__ __forceinline__ void mma_bf16(float* d, uint32_t a0, uint32_t a1, uint32_t a2, uint32_t a3, uint32_t b0, uint32_t b1) {
    asm volatile("mma.sync.aligned.m16n8k16.row.col.f32.bf16.bf16.f32 {%0,%1,%2,%3}, {%4,%5,%6,%7}, {%8,%9}, {%0,%1,%2,%3};"
                 : "+f"(d[0]), "+f"(d[1]), "+f"(d[2]), "+f"(d[3]) : "r"(a0), "r"(a1), "r"(a2), "r"(a3), "r"(b0), "r"(b1));
}
__device__ __forceinline__ void mma_bf16_k8(float* d, uint32_t a0, uint32_t a1, uint32_t b0) {
    asm volatile("mma.sync.aligned.m16n8k8.row.col.f32.bf16.bf16.f32 {%0,%1,%2,%3}, {%4,%5}, {%6}, {%0,%1,%2,%3};"
                 : "+f"(d[0]), "+f"(d[1]), "+f"(d[2]), "+f"(d[3]) : "r"(a0), "r"(a1), "r"(b0));
}
__device__ __forceinline__ void ldsm_x4(uint32_t* r, uint32_t addr) {
    asm volatile("ldmatrix.sync.aligned.m8n8.x4.shared.b16 {%0,%1,%2,%3}, [%4];"
                 : "=r"(r[0]), "=r"(r[1]), "=r"(r[2]), "=r"(r[3]) : "r"(addr));
}

__device__ __forceinline__ void ldsm_x4_t(uint32_t* r, uint32_t addr) {
    asm volatile("ldmatrix.sync.aligned.m8n8.x4.trans.shared.b16 {%0,%1,%2,%3}, [%4];"
                 : "=r"(r[0]), "=r"(r[1]), "=r"(r[2]), "=r"(r[3]) : "r"(addr));
}
__device__ __forceinline__ void mbar_init(uint32_t bar, int count) { asm volatile("mbarrier.init.shared::cta.b64 [%0], %1;" ::"r"(bar), "r"(count)); }
__device__ __forceinline__ void mbar_arrive(uint32_t bar) { asm volatile("mbarrier.arrive.shared::cta.b64 _, [%0];" ::"r"(bar) : "memory"); }
__device__ __forceinline__ void mbar_wait(uint32_t bar, uint32_t parity) {
    asm volatile("{\n.reg .pred p;\nWAIT_LOOP:\n"
                 "mbarrier.try_wait.parity.shared::cta.b64 p, [%0], %1;\n"
                 "@p bra.uni WAIT_DONE;\nbra.uni WAIT_LOOP;\nWAIT_DONE:\n}" ::"r"(bar), "r"(parity) : "memory");
}

__device__ __forceinline__ void mbar_expect_tx(uint32_t bar, uint32_t bytes) {
    asm volatile("mbarrier.arrive.expect_tx.shared::cta.b64 _, [%0], %1;" ::"r"(bar), "r"(bytes) : "memory");
}
__device__ __forceinline__ void tma_load_2d(uint32_t dst, const void* tmap, int c0, int c1, uint32_t bar) {
    asm volatile("cp.async.bulk.tensor.2d.shared::cluster.global.mbarrier::complete_tx::bytes [%0], [%1, {%3, %4}], [%2];"
                 ::"r"(dst), "l"(tmap), "r"(bar), "r"(c0), "r"(c1) : "memory");
}
__device__ __forceinline__ void tma_load_3d(uint32_t dst, const void* tmap, int c0, int c1, int c2, uint32_t bar) {
    asm volatile("cp.async.bulk.tensor.3d.shared::cluster.global.mbarrier::complete_tx::bytes [%0], [%1, {%3, %4, %5}], [%2];"
                 ::"r"(dst), "l"(tmap), "r"(bar), "r"(c0), "r"(c1), "r"(c2) : "memory");
}
__device__ __forceinline__ void fence_async_smem() { asm volatile("fence.proxy.async.shared::cta;" ::: "memory"); }
__device__ __forceinline__ void bulk_load(uint32_t dst, const void* src, uint32_t bytes, uint32_t bar) {
    asm volatile("cp.async.bulk.shared::cluster.global.mbarrier::complete_tx::bytes [%0], [%1], %2, [%3];"
                 ::"r"(dst), "l"(src), "r"(bytes), "r"(bar) : "memory");
}
__device__ __forceinline__ void stsm_x4(uint32_t addr, uint32_t r0, uint32_t r1, uint32_t r2, uint32_t r3) {
    asm volatile("stmatrix.sync.aligned.m8n8.x4.shared.b16 [%0], {%1,%2,%3,%4};" ::"r"(addr), "r"(r0), "r"(r1), "r"(r2), "r"(r3) : "memory");
}
__device__ __forceinline__ void stsm_x4_t(uint32_t addr, uint32_t r0, uint32_t r1, uint32_t r2, uint32_t r3) {
    asm volatile("stmatrix.sync.aligned.m8n8.x4.trans.shared.b16 [%0], {%1,%2,%3,%4};" ::"r"(addr), "r"(r0), "r"(r1), "r"(r2), "r"(r3) : "memory");
}
__device__ __forceinline__ void prefetch_tmap(const void* tmap) { asm volatile("prefetch.tensormap [%0];" ::"l"(tmap) : "memory"); }

__device__ __forceinline__ float2 cexp_at(float wr2, float wi, float p) {
    float er;
    asm("ex2.approx.ftz.f32 %0, %1;" : "=f"(er) : "f"(wr2 * p));
    float th = wi * p;
    const float k = rintf(th * 0.15915494309189535f);
    th = fmaf(k, -6.2831854820251465f, th);
    th = fmaf(k, 1.7484555314695172e-7f, th);
    return make_float2(er * __cosf(th), er * __sinf(th));
}
__device__ __forceinline__ float2 cmul(float2 a, float2 b) {
    return make_float2(fmaf(a.x, b.x, -a.y * b.y), fmaf(a.x, b.y, a.y * b.x));
}
__device__ __forceinline__ float2 csqr(float2 a) { return make_float2(fmaf(a.x, a.x, -a.y * a.y), (a.x + a.x) * a.y); }
__device__ __forceinline__ uint32_t packh(float2 v) {
    uint32_t r;
    asm("cvt.rn.f16x2.f32 %0, %1, %2;" : "=r"(r) : "f"(v.y), "f"(v.x));
    return r;
}
__device__ __forceinline__ void mma_f16(float* d, uint32_t a0, uint32_t a1, uint32_t a2, uint32_t a3, uint32_t b0, uint32_t b1) {
    asm volatile("mma.sync.aligned.m16n8k16.row.col.f32.f16.f16.f32 {%0,%1,%2,%3}, {%4,%5,%6,%7}, {%8,%9}, {%0,%1,%2,%3};"
                 : "+f"(d[0]), "+f"(d[1]), "+f"(d[2]), "+f"(d[3]) : "r"(a0), "r"(a1), "r"(a2), "r"(a3), "r"(b0), "r"(b1));
}

struct KgIn { const bf16 *logA, *Aim, *Cre, *Cim, *logdt, *dsk, *x, *wqkv, *wo; uint4 *tap, *wq, *wop, *halo, *sum; float* csp; };
constexpr int KG_THREADS = NMODE / 2;

constexpr int KG_BUF = 15 * 12288, KG_BAR = KG_BUF + 6 * 5120, KG_SMEM = KG_BAR + 64;
__global__ void __launch_bounds__(512, 1) kgen_kernel(const KgIn in, const __grid_constant__ CUtensorMap tmWq, const __grid_constant__ CUtensorMap tmWo,
                                                        const __grid_constant__ CUtensorMap tmWt) {
    extern __shared__ __align__(1024) uint4 tabs[];
#define KG_ROT 0
    const int lane = threadIdx.x & 31, w16 = (__shfl_sync(~0u, threadIdx.x >> 5, 0) + KG_ROT) & 15, grp = w16 / 3, warp = w16 - 3 * grp;
    const int d = blockIdx.x * 5 + grp, tid = warp * 32 + lane;
    uint4* tab = tabs + grp * (3 * 768);
    SPAN(0, 0); SPAN(0, 1);
    TSTAMPK(0, 0);
    asm volatile("griddepcontrol.launch_dependents;" ::: "memory");
    if (w16 == 15) {
        const uint32_t b0 = smem_u32(tab), wbar = b0 + 6 * 5120;
        const int blk = blockIdx.x, nq = blk < 112 ? 4 : 2, nj = nq + (blk < 64 ? 1 : 2);
        auto fetch = [&](int i) {
            const uint32_t dst = b0 + i * 5120, bar = wbar + 8 * i;
            if (i < nq) {
                const int p = blk + 64 * (i & 2), kb = p / 24;
                mbar_expect_tx(bar, 5120);
                tma_load_3d(dst, &tmWq, 0, kb * 64 + (i & 1) * 32, (p - 24 * kb) * 5, bar);
            } else if (i < nj) {
                const int o = i == nq ? blk : 255 - blk;
                mbar_expect_tx(bar, o < 128 ? 5120 : 2560);
                asm volatile("cp.async.bulk.tensor.5d.shared::cluster.global.mbarrier::complete_tx::bytes [%0], [%1, {%3, %3, %4, %3, %5}], [%2];"
                             ::"r"(dst), "l"(o < 128 ? &tmWo : &tmWt), "r"(bar), "r"(0), "r"((o & 7) * 10 + (o >> 6) * 4), "r"(((o >> 3) & 7) * 5) : "memory");
            }
        };
        const bool one = elect();
        if (one) {
#pragma unroll
            for (int i = 0; i < 6; i++) mbar_init(wbar + 8 * i, 1);
            asm volatile("fence.mbarrier_init.release.cluster;" ::: "memory");
#pragma unroll
            for (int i = 0; i < 6; i++) fetch(i);
        }
        __syncwarp();
#pragma unroll
        for (int i = 1; i <= 5; i++) asm volatile("bar.arrive %0, 128;" ::"r"(i) : "memory");
        if (one) {
#pragma unroll 1
            for (int i = 0; i < nj; i++) {
                const int p = blk + 64 * (i & 2), kb = p / 24, hg = p & 7, sec = (p - 24 * kb) >> 3, o = i == nq ? blk : 255 - blk, cg = (o >> 3) & 7, hb = o & 7;
                const unsigned char* dst = i < nq ? reinterpret_cast<unsigned char*>(in.wq) + (hg * 10 + (hg < 4 ? kb : kb < 5 ? kb + 5 : kb - 5)) * WQ_STAGE + ((i & 1) * 3 + sec) * 5120
                                                  : reinterpret_cast<unsigned char*>(in.wop) + (cg * 8 + (hb == cg ? 0 : hb + (hb < cg))) * WOB + (o >> 6) * 5120;
                mbar_wait(wbar + 8 * i, 0);
                if (i == 0) TSTAMPK(2, (15 - KG_ROT) * 32);
                if (i == 3) TSTAMPK(5, (15 - KG_ROT) * 32);
                asm volatile("cp.async.bulk.global.shared::cta.bulk_group [%0], [%1], %2;" ::"l"(dst), "r"(b0 + i * 5120), "r"(i < nq || o < 128 ? 5120 : 2560) : "memory");
            }
            asm volatile("cp.async.bulk.commit_group;" ::: "memory");
            asm volatile("cp.async.bulk.wait_group.read 0;" ::: "memory");
        }
        TSTAMPK(11, (15 - KG_ROT) * 32);
        return;
    }
    const bf16 pdt = in.logdt[d], pdsk = in.dsk[d];
    const uint32_t pla = reinterpret_cast<const uint32_t*>(in.logA)[d * KG_THREADS + tid], pai = reinterpret_cast<const uint32_t*>(in.Aim)[d * KG_THREADS + tid];
    const uint32_t pcr = reinterpret_cast<const uint32_t*>(in.Cre)[d * KG_THREADS + tid], pci = reinterpret_cast<const uint32_t*>(in.Cim)[d * KG_THREADS + tid];
    const bf16* pfq = tid < 30 ? in.wqkv + (size_t)(d * 30 + tid) * 64 : tid < 40 ? in.wo + (size_t)(d * 10 + tid - 30) * 64 : in.x + (size_t)(d * 32 + tid - 40) * 64;
#define KG_PF 0
    if (tid < (KG_PF == 3 ? 0 : KG_PF ? 40 : 72)) asm volatile("prefetch.global.L2 [%0];" ::"l"(pfq));
    asm volatile("st.global.v4.u32 [%0], {%1,%1,%1,%1};" ::"l"(in.halo + d * 148 + tid), "r"(~0u));
    if (tid < 52) asm volatile("st.global.v4.u32 [%0], {%1,%1,%1,%1};" ::"l"(in.halo + d * 148 + 96 + tid), "r"(~0u));
    else if (w16 == 2) {
        if (lane < 16) in.sum[blockIdx.x * 16 + lane] = make_uint4(0, 0, 0, 0);
        else if (lane < 20) reinterpret_cast<uint32_t*>(in.sum + 2048)[(blockIdx.x * 4 + lane - 16) * FSTR] = 0;
    }
    const uint32_t tw = smem_u32(tab) + warp * 12288;
    const int g = lane >> 2, t = lane & 3;
    const uint32_t sta = tw + lane * 128 + ((2 * (lane & 3) + ((lane >> 2) & 1)) << 4);
    const uint32_t lda = tw + t * 128 + ((g ^ (2 * t)) << 4);
    const uint32_t stb = tw + lane * 8, ldb = tw + g * 512 + (g & 3) * 32 + t * 8;
    auto sts4 = [&](int e, int off, uint32_t a, uint32_t b, uint32_t c, uint32_t dd) {
        asm volatile("st.shared.v4.u32 [%0], {%1,%2,%3,%4};" ::"r"((sta ^ (e << 4)) + off), "r"(a), "r"(b), "r"(c), "r"(dd) : "memory");
    };
    auto lds4 = [&](int sp, int off, uint32_t* r) {
        asm volatile("ld.shared.v4.u32 {%0,%1,%2,%3}, [%4];" : "=r"(r[0]), "=r"(r[1]), "=r"(r[2]), "=r"(r[3]) : "r"((lda ^ ((sp & 1) << 4)) + sp * 512 + off) : "memory");
    };
    const float dt = rbf(expf(bf2f(pdt)));
    float2 C[2], y1[2], z8[2], y128[2];
    float cmax = 0.f;
#pragma unroll
    for (int m = 0; m < 2; m++) {
        const float wr2 = -rbf(expf(__uint_as_float(m ? pla & 0xffff0000u : pla << 16))) * dt * 1.4426950408889634f;
        const float wi = __uint_as_float(m ? pai & 0xffff0000u : pai << 16) * dt;
        C[m] = make_float2(__uint_as_float(m ? pcr & 0xffff0000u : pcr << 16) * dt, -__uint_as_float(m ? pci & 0xffff0000u : pci << 16) * dt);
        cmax = fmaxf(cmax, fmaxf(fabsf(C[m].x), fabsf(C[m].y)));
        y1[m] = cexp_at(wr2, -wi, 1.f); z8[m] = cexp_at(wr2, wi, 8.f); y128[m] = cexp_at(wr2, -wi, 128.f);
    }
    const int ex = min(max((int)(__reduce_max_sync(~0u, __float_as_uint(cmax)) >> 23), 20), 240);
    const float scale = __uint_as_float((uint32_t)(127 + 10 + 127 - ex) << 23), unscale = 2.0f * __uint_as_float((uint32_t)(ex - 10) << 23);
    TSTAMPK(4, 64);
    if (KG_PF >= 2 && tid >= 40 && tid < 72) asm volatile("prefetch.global.L2 [%0];" ::"l"(pfq));
    float k2048 = 0.f;
    float acc[5][4];
#pragma unroll
    for (int j = 0; j < 5; j++)
#pragma unroll
        for (int k = 0; k < 4; k++) acc[j][k] = 0.f;
    uint32_t af[8][4];
    {
        float2 h0[2], h1[2], g0[2], g1[2], g2[2], g2b[2], g3[2], g4[2], y2[2], y4[2];
#pragma unroll
        for (int m = 0; m < 2; m++) {
            h0[m] = make_float2(1.f, 0.f); h1[m] = csqr(csqr(csqr(z8[m])));
            g0[m] = make_float2(C[m].x * scale, C[m].y * scale);
            g1[m] = cmul(g0[m], y128[m]);
            const float2 y256 = csqr(y128[m]), y512 = csqr(y256);
            g2b[m] = g2[m] = cmul(g0[m], y256); g3[m] = cmul(g0[m], y512); g4[m] = cmul(g3[m], y512);
            y2[m] = csqr(y1[m]); y4[m] = csqr(y2[m]);
            const float2 y1024 = csqr(y512);
            k2048 += fmaf(g4[m].x, y1024.x, -g4[m].y * y1024.y);
        }
#pragma unroll
        for (int e = 0; e < 8; e++) {
            sts4(e, 0, packh(h0[0]), packh(h1[0]), packh(h0[1]), packh(h1[1]));
            sts4(e, 4096, packh(g0[0]), packh(g0[1]), packh(g1[0]), packh(g1[1]));
#pragma unroll
            for (int m = 0; m < 2; m++)
                if (e < 7) { h0[m] = e ? cmul(h0[m], z8[m]) : z8[m]; h1[m] = cmul(h1[m], z8[m]); g0[m] = cmul(g0[m], y1[m]); g1[m] = cmul(g1[m], y1[m]); }
            if (e < 5) k2048 += __shfl_xor_sync(~0u, k2048, 1 << e);
        }
        if (KG_PF == 1 && tid >= 40 && tid < 72) asm volatile("prefetch.global.L2 [%0];" ::"l"(pfq));
        __syncwarp();
#pragma unroll
        for (int e = 0; e < 8; e++) {
            uint32_t b[4];
            lds4(e, 0, af[e]); lds4(e, 4096, b);
            sts4(e, 8192, packh(g2[0]), packh(g2[1]), packh((e & 1) ? cmul(g3[0], y4[0]) : g3[0]), packh((e & 1) ? cmul(g3[1], y4[1]) : g3[1]));
            asm volatile("st.shared.v2.u32 [%0], {%1,%2};" ::"r"((stb ^ ((e & 3) << 5)) + e * 512), "r"(packh(g4[0])), "r"(packh(g4[1])) : "memory");
#pragma unroll
            for (int m = 0; m < 2; m++)
                if (e < 7) {
                    g2[m] = e == 3 ? cmul(g2b[m], y128[m]) : cmul(g2[m], y2[m]);
                    if (e & 1) g3[m] = cmul(g3[m], y128[m]);
                    g4[m] = cmul(g4[m], y128[m]);
                }
            mma_f16(acc[0], af[e][0], af[e][1], af[e][2], af[e][3], b[0], b[1]);
            mma_f16(acc[1], af[e][0], af[e][1], af[e][2], af[e][3], b[2], b[3]);
        }
    }
    TSTAMPK(6, 64);
    __syncwarp();
#pragma unroll
    for (int sp = 0; sp < 8; sp++) {
        uint32_t c[4], e0, e1;
        lds4(sp, 8192, c);
        asm volatile("ld.shared.v2.u32 {%0,%1}, [%2];" : "=r"(e0), "=r"(e1) : "r"(ldb ^ (sp << 5)) : "memory");
        mma_f16(acc[2], af[sp][0], af[sp][1], af[sp][2], af[sp][3], c[0], c[1]);
        mma_f16(acc[3], af[sp][0], af[sp][1], af[sp][2], af[sp][3], c[2], c[3]);
        mma_f16(acc[4], af[sp][0], af[sp][1], af[sp][2], af[sp][3], e0, e1);
    }
    {
        float* Pp = reinterpret_cast<float*>(tab + warp * 768);
        auto sw = [](int i) { return i ^ ((i >> 2) & 24); };
#pragma unroll
        for (int h = 0; h < 2; h++) {
            const int b = g + 8 * h;
            *reinterpret_cast<float2*>(Pp + sw(8 * b + 2 * t)) = make_float2(acc[0][2 * h] * unscale, acc[0][2 * h + 1] * unscale);
            *reinterpret_cast<float2*>(Pp + 128 + sw(8 * b + 2 * t)) = make_float2(acc[1][2 * h] * unscale, acc[1][2 * h + 1] * unscale);
            *reinterpret_cast<float2*>(Pp + 256 + sw(4 * b + 2 * (t & 1) + 64 * (t >> 1))) = make_float2(acc[2][2 * h] * unscale, acc[2][2 * h + 1] * unscale);
            *reinterpret_cast<float2*>(Pp + 384 + sw(2 * b + 32 * t)) = make_float2(acc[3][2 * h] * unscale, acc[3][2 * h + 1] * unscale);
            Pp[512 + sw(b + 32 * t)] = acc[4][2 * h] * unscale;
            Pp[512 + sw(b + 32 * t + 16)] = acc[4][2 * h + 1] * unscale;
        }
        if (lane == 0) Pp[640] = k2048 * unscale;
    }
    TSTAMPK(7, 64);
    asm volatile("bar.sync %0, 128;" ::"r"(grp + 1) : "memory");
    TSTAMPK(9, 64);
    const float* Kp = reinterpret_cast<const float*>(tab);
    auto ksum = [&](int i) -> float { return (Kp[i] + Kp[3072 + i]) + Kp[6144 + i]; };
    auto ksum4 = [&](int q) -> float4 {
        q ^= (q >> 2) & 6;
        const float4 a = reinterpret_cast<const float4*>(Kp)[q], b = reinterpret_cast<const float4*>(Kp)[768 + q], c = reinterpret_cast<const float4*>(Kp)[1536 + q];
        return make_float4((a.x + b.x) + c.x, (a.y + b.y) + c.y, (a.z + b.z) + c.z, (a.w + b.w) + c.w);
    };
    {
        uint2* E4 = reinterpret_cast<uint2*>(in.tap + d * 128);
        float4 v = ksum4(tid), u = ksum4(96 + min(tid, 64));
        const float cor = rbf(ksum(tid == 95 ? 384 : 512));
        if (tid == 0) v.x += bf2f(pdsk);
        if (tid == 95) v.w -= cor;
        if (tid == 31) u.w -= cor;
        const uint32_t lo = pack2(v.x, v.y), hi = pack2(v.z, v.w);
        if (tid < 64) {
            E4[6 + tid] = make_uint2(lo, hi);
            E4[(tid < 32 ? 159 : 209 - 32) + tid] = make_uint2(pack2(u.x, u.y), pack2(u.z, u.w));
        } else {
            const uint32_t nx = __shfl_down_sync(~0u, lo, 1);
            in.tap[d * 128 + 35 + tid - 64] = make_uint4(__byte_perm(lo, 0, 0x1010), __byte_perm(lo, hi, 0x5432), __byte_perm(hi, 0, 0x1010), __byte_perm(hi, tid == 95 ? 0u : nx, 0x5432));
            if (tid == 64) E4[241] = make_uint2(pack2(u.x, 0.f), 0u);
        }
    }
    TSTAMPK(10, 64);
    if (warp < (blockIdx.x < 112 ? 2 : 1)) {
        const uint32_t sb = smem_u32(tabs);
        mbar_wait(sb + KG_BAR + 16 * warp, 0); mbar_wait(sb + KG_BAR + 16 * warp + 8, 0);
        uint32_t w[4][4];
        float cs[4] = {0.f, 0.f, 0.f, 0.f};
#pragma unroll
        for (int a = 0; a < 4; a++)
            ldsm_x4_t(w[a], sb + KG_BUF + warp * 10240 + grp * 1024 + ((lane >> 4) * 8 + (lane & 7)) * 32 + ((((lane >> 3) ^ (lane >> 2)) & 1) << 4) + (a >> 1) * 5120 + (a & 1) * 512);
#pragma unroll
        for (int a = 0; a < 4; a++) mma_bf16(cs, w[a][0], w[a][1], w[a][2], w[a][3], 0x3f803f80u, 0x3f803f80u);
        if (t < 2) in.csp[(blockIdx.x + 128 * warp) * 80 + grp * 16 + g + 8 * t] = t ? cs[2] : cs[0];
    }
    SPAN(0, 3);
}

#define CV_SLEEP 100
#define CV_D2 3
#define CV_PDH 12
#define CV_PDF 4
#define CV_HAND 7
constexpr int CV_CPB = 5;
constexpr int CV_THREADS = 512;
constexpr int UPADF = 128;
constexpr int ULEN = UPADF + SEQ;
constexpr int XLEN = SEQ + 16;
constexpr int BX_5 = 0, BX_3 = 3264, BX_9 = 6528, BX_7 = 8960, BX_LEN = 11392;
constexpr int CV_SM_U = 0;
constexpr int CV_SM_T = CV_CPB * ULEN * 2;
constexpr int CV_SM_B = CV_SM_T + CV_CPB * TAPB;
constexpr int CV_SM_X = CV_SM_B + CV_CPB * BX_LEN;
constexpr int CV_SM_Y = (CV_SM_X + CV_CPB * XLEN * 2 + 127) & ~127;
constexpr int CV_SM_CNT = CV_SM_Y + CV_CPB * 8192;
constexpr int CV_SM_O = CV_SM_CNT + 128;
constexpr int CV_SMEM = CV_SM_O + 20480 + CST_EXTRA;
static_assert(ULEN % 128 == 0 && CV_SM_B % 128 == 0 && CV_SM_CNT % 128 == 0, "layout");

__device__ __forceinline__ uint32_t sub2(uint32_t x, uint32_t m) {
    const __nv_bfloat162 d = __hsub2(*reinterpret_cast<const __nv_bfloat162*>(&x), *reinterpret_cast<const __nv_bfloat162*>(&m));
    return *reinterpret_cast<const uint32_t*>(&d);
}
__device__ __forceinline__ uint32_t add2(uint32_t x, uint32_t y) {
    const __nv_bfloat162 d = __hadd2_rn(*reinterpret_cast<const __nv_bfloat162*>(&x), *reinterpret_cast<const __nv_bfloat162*>(&y));
    return *reinterpret_cast<const uint32_t*>(&d);
}
__device__ __forceinline__ void wgmma_fence() { asm volatile("wgmma.fence.sync.aligned;" ::: "memory"); }
__device__ __forceinline__ void wgmma_commit() { asm volatile("wgmma.commit_group.sync.aligned;" ::: "memory"); }
template <int N> __device__ __forceinline__ void wgmma_wait() { asm volatile("wgmma.wait_group.sync.aligned %0;" ::"n"(N) : "memory"); }
__device__ __forceinline__ uint64_t make_desc(uint32_t addr, uint32_t lbo, uint32_t sbo, uint32_t mode) {
    return (uint64_t)((addr & 0x3FFFF) >> 4) | ((uint64_t)(lbo >> 4) << 16) | ((uint64_t)(sbo >> 4) << 32) | ((uint64_t)mode << 62);
}
__device__ __forceinline__ void wgmma_rs128(float (&d)[64], uint2 hi, uint2 lo, uint64_t db, int acc) {
    asm volatile("{\n.reg .pred p;\nsetp.ne.b32 p, %69, 0;\nwgmma.mma_async.sync.aligned.m64n128k16.f32.bf16.bf16 {%0,%1,%2,%3,%4,%5,%6,%7,%8,%9,%10,%11,%12,%13,%14,%15,%16,%17,%18,%19,%20,%21,%22,%23,%24,%25,%26,%27,%28,%29,%30,%31,%32,%33,%34,%35,%36,%37,%38,%39,%40,%41,%42,%43,%44,%45,%46,%47,%48,%49,%50,%51,%52,%53,%54,%55,%56,%57,%58,%59,%60,%61,%62,%63}, {%64,%65,%66,%67}, %68, p, 1, 1, 0;\n}"
                 : "+f"(d[0]), "+f"(d[1]), "+f"(d[2]), "+f"(d[3]), "+f"(d[4]), "+f"(d[5]), "+f"(d[6]), "+f"(d[7]), "+f"(d[8]), "+f"(d[9]), "+f"(d[10]), "+f"(d[11]), "+f"(d[12]), "+f"(d[13]), "+f"(d[14]), "+f"(d[15]), "+f"(d[16]), "+f"(d[17]), "+f"(d[18]), "+f"(d[19]), "+f"(d[20]), "+f"(d[21]), "+f"(d[22]), "+f"(d[23]), "+f"(d[24]), "+f"(d[25]), "+f"(d[26]), "+f"(d[27]), "+f"(d[28]), "+f"(d[29]), "+f"(d[30]), "+f"(d[31]), "+f"(d[32]), "+f"(d[33]), "+f"(d[34]), "+f"(d[35]), "+f"(d[36]), "+f"(d[37]), "+f"(d[38]), "+f"(d[39]), "+f"(d[40]), "+f"(d[41]), "+f"(d[42]), "+f"(d[43]), "+f"(d[44]), "+f"(d[45]), "+f"(d[46]), "+f"(d[47]), "+f"(d[48]), "+f"(d[49]), "+f"(d[50]), "+f"(d[51]), "+f"(d[52]), "+f"(d[53]), "+f"(d[54]), "+f"(d[55]), "+f"(d[56]), "+f"(d[57]), "+f"(d[58]), "+f"(d[59]), "+f"(d[60]), "+f"(d[61]), "+f"(d[62]), "+f"(d[63])
                 : "r"(hi.x), "r"(hi.y), "r"(lo.x), "r"(lo.y), "l"(db), "r"(acc));
}
template <int V> struct Int { __device__ constexpr operator int() const { return V; } };
__device__ __forceinline__ void sts4(uint32_t a, const uint32_t* v) { asm volatile("st.shared.v4.u32 [%0], {%1,%2,%3,%4};" ::"r"(a), "r"(v[0]), "r"(v[1]), "r"(v[2]), "r"(v[3]) : "memory"); }
__device__ __forceinline__ uint32_t lds1(uint32_t a) { uint32_t v; asm volatile("ld.shared.u32 %0, [%1];" : "=r"(v) : "r"(a) : "memory"); return v; }
__device__ __forceinline__ uint4 lds4(uint32_t a) { uint4 v; asm volatile("ld.shared.v4.u32 {%0,%1,%2,%3}, [%4];" : "=r"(v.x), "=r"(v.y), "=r"(v.z), "=r"(v.w) : "r"(a) : "memory"); return v; }
__device__ __forceinline__ void cv_store(unsigned char* p, uint4 x, uint4 y) {
    asm volatile("st.relaxed.gpu.global.v2.u32 [%0], {%1,%2};" ::"l"(p), "r"(add2(x.x, __byte_perm(y.x, y.y, 0x5410))), "r"(add2(x.y, __byte_perm(y.z, y.w, 0x5410))) : "memory");
    asm volatile("st.relaxed.gpu.global.v2.u32 [%0], {%1,%2};" ::"l"(p + 128), "r"(add2(x.z, __byte_perm(y.x, y.y, 0x7632))), "r"(add2(x.w, __byte_perm(y.z, y.w, 0x7632))) : "memory");
}
__device__ __forceinline__ int usw(int ch) { return ch ^ ((ch >> 3) & 1); }
__global__ void __launch_bounds__(CV_THREADS, 1) conv_kernel(int layer, const uint4* __restrict__ piv, const float4* __restrict__ sum, const bf16* __restrict__ x1T,
                                                             bf16* __restrict__ dst, const uint4* __restrict__ tap, const __grid_constant__ CUtensorMap tmOut) {
    extern __shared__ __align__(1024) unsigned char sm[];
    SPAN(3 + 4 * layer, 0);
    bf16* Us = reinterpret_cast<bf16*>(sm + CV_SM_U);
    bf16* Xs = reinterpret_cast<bf16*>(sm + CV_SM_X);
#define CV_IDX int tid; asm volatile("mov.u32 %0, %tid.x;" : "=r"(tid)); const int lane = tid & 31, warp = __shfl_sync(~0u, tid >> 5, 0);
    const int d0 = blockIdx.x * CV_CPB, tile = blockIdx.x; (void)tile;
    const uint32_t cnt = smem_u32(sm + CV_SM_CNT);
    struct Lc { uint32_t a4, a8, uc, ud, y, e4, en, sp, ss; int go; };
    auto lane_consts = [&](int lane, int c) {
        const int mat = lane >> 3, r = lane & 7, g = lane >> 2, ti = lane & 3, e = g - 2 * ti;
        const int j2 = 13 + (r ^ 1) + 8 * (mat >> 1), j3 = j2 + 2, i0 = 8 * (mat & 1);
        const uint32_t sb = smem_u32(sm), oc = sb + usw(16 * (mat >> 1) + 2 * r + (mat & 1)) * 16;
        const Lc l = {sb + CV_SM_B + c * BX_LEN + ((j2 & 1) ? BX_3 + (4 * j2 + i0 + 84) * 2 : BX_5 + (4 * j2 + i0 + 80) * 2),
                      sb + CV_SM_B + c * BX_LEN + ((j3 & 1) ? BX_7 : BX_9) + (8 * j3 + i0 + 136) * 2,
                      oc + CV_SM_U + (c * ULEN + UPADF) * 2, sb + CV_SM_U + (c * ULEN + UPADF) * 2 + usw(16 * mat + 2 * r + 2) * 16, oc + CV_SM_Y + c * 8192,
                      sb + CV_SM_O + 2048 * c + (307 + 2 * g - ti) * 4, sb + CV_SM_T + c * TAPB + (152 + 144 + e) * 8 + 4,
                      e == -5 ? 0x4410u : e == -4 ? 0x1044u : 0x4444u, e == 3 ? 0x4410u : e == 4 ? 0x1044u : 0x4444u,
                      c * XCP * 2 + (lane >> 4) * 256 + (lane & 15) * 8};
        asm volatile("st.shared.u32 [%0], %1;" ::"r"(l.y), "r"(l.a4 ^ l.a8 ^ l.uc ^ l.ud ^ l.e4 ^ l.en ^ l.sp ^ l.ss ^ l.go) : "memory");
        return l;
    };
    unsigned char* const dq = reinterpret_cast<unsigned char*>(dst + (size_t)d0 * XCP);
    auto far = [&](auto T0_, const auto& seq, const Lc& lc, int c, int lane, const uint2 (&f)[20], uint32_t kk) {
        constexpr int T0 = T0_, T1 = T0 + 6, TC = T0 > 7 ? T0 : 7, NS = sizeof(seq) / sizeof(seq[0]), PD = T0 > 7 ? CV_PDH : CV_PDF;
        uint32_t bq[28], yw[4], yz[4], P, S;
        uint4 xv, yv;
        asm("prmt.b32 %0, %1, 0, %2;" : "=r"(P) : "r"(kk), "r"(lc.sp));
        asm("prmt.b32 %0, %1, 0, %2;" : "=r"(S) : "r"(kk), "r"(lc.ss));
#pragma unroll
        for (int k = 0; 2 * k < T1 - TC + 4; k++) ldsm_x4(bq + 4 * k, lc.uc + (TC - 8) * 256 + 512 * k);
#pragma unroll
        for (int k = 0; 4 * k < T1 - TC; k++) ldsm_x4(bq + 20 + 4 * k, lc.ud + (TC - 8) * 256 + 1024 * k);
        CST(3);
        mbar_wait(cnt + 8 * c, 0);
        mbar_wait(cnt + 40, 0);
        CST(4);
        float acc[6][4] = {};
        uint32_t a[PD + 1][4];
#pragma unroll
        for (int i = -PD; i < NS + 3; i++) {
            if (i + PD < NS) ldsm_x4_t(a[(i + PD) % (PD + 1)], seq[i + PD] < 32 ? lc.a4 + (seq[i + PD] - 2) * 128 : lc.a8 + (seq[i + PD] - 34) * 256);
            if (i < 0) continue;
#pragma unroll
            for (int T = T0; T < T1; T++) {
                if (i >= NS) break;
                const int ee = seq[i] < 32 ? 2 * T - 6 - seq[i] : T + 35 - seq[i];
                if (i == 0 && T >= TC) mma_bf16(acc[T - T0], P, 0u, S, P, bq[2 * (T - TC)], bq[2 * (T - TC) + 1]);
                if (i == 1 && T >= TC) mma_bf16_k8(acc[T - T0], 0u, S, bq[20 + T - TC]);
                if (i == (T >= TC ? 2 : 0)) mma_bf16(acc[T - T0], f[19].x, 0u, f[19].y, f[19].x, bq[2 * (T - TC + 4)], bq[2 * (T - TC + 4) + 1]);
                if (seq[i] < 32 ? ee >= 0 && ee <= 9 : ee >= 10) mma_bf16(acc[T - T0], a[i % (PD + 1)][0], a[i % (PD + 1)][1], a[i % (PD + 1)][2], a[i % (PD + 1)][3], f[ee].x, f[ee].y);
            }
#pragma unroll
            for (int k = 0; k < 3; k++) {
                const int o = 256 * T0 + 512 * k;
                auto at = [&](int d) { return i - d >= 0 && i - d < NS && seq[i - d < 0 ? 0 : i - d < NS ? i - d : 0] == 2 * T0 + 4 * k - 4; };
                if (at(CV_D2)) {
                    cv_store(dq + lc.go + o, xv, yv);
                    if (layer > 19 - 2 * k) __trap();
                }
                if (at(-2)) { ldsm_x4_t(yw, lc.y + o); ldsm_x4_t(yz, lc.y + 3584 + o); }
                if (at(1)) {
#pragma unroll
                    for (int q = 0; q < 4; q++) yw[q] = add2(add2(yw[q], yz[q]), pack2(acc[2 * k + (q >> 1)][2 * (q & 1)], acc[2 * k + (q >> 1)][2 * (q & 1) + 1]));
                    stsm_x4_t(lc.y + o, yw[0], yw[1], yw[2], yw[3]);
                    xv = lds4(smem_u32(Xs + c * XLEN) + o + lane * 16);
                    __syncwarp();
                    yv = lds4(smem_u32(sm + CV_SM_Y) + c * 8192 + o + usw(lane) * 16);
                    if (layer > 20 - 2 * k) __trap();
                    if (k == 2) CST(6);
                }
            }
        }
    };
    TSTAMP1X(9, 256);
    if (threadIdx.x >= 256) {
        CV_IDX
        const int t2 = tid - 256, wgu = (warp >> 2) & 1, g = lane >> 2, ti = lane & 3;
        if (t2 == 0) {
            mbar_init(cnt + 48, 1);
            asm volatile("fence.mbarrier_init.release.cluster;" ::: "memory");
            mbar_expect_tx(cnt + 48, CV_CPB * 2048);
            bulk_load(smem_u32(sm + CV_SM_O), tap + d0 * 128, CV_CPB * 2048, cnt + 48);
        } else if (lane == 0) {
            if (warp < 15) mbar_init(cnt + 8 * (warp - 9), warp == 14 ? 8 : 4);
            else if (layer) prefetch_tmap(&tmOut);
        }
        if (t2 < 140) {
            const int k = t2;
            const int off = k < 20 ? CV_SM_B + BX_5 + 8 * k : k < 40 ? CV_SM_B + BX_3 + 8 * (k - 20) : k < 74 ? CV_SM_B + BX_9 + 8 * (k - 40) : k < 108 ? CV_SM_B + BX_7 + 8 * (k - 74) : CV_SM_U + 8 * (k - 108);
            const int str = k < 108 ? BX_LEN : ULEN * 2;
#pragma unroll
            for (int c = 0; c < CV_CPB; c++) *reinterpret_cast<uint2*>(sm + off + c * str) = make_uint2(0, 0);
        }
        fence_async_smem();
        asm volatile("bar.arrive 3, 512;" ::: "memory");
        asm volatile("bar.sync 1, 256;" ::: "memory");
        TSTAMP1X(10, 256);
        asm volatile("setmaxnreg.inc.sync.aligned.u32 168;");
        const int hc = wgu ? warp & 3 : 4;
        const Lc lc = lane_consts(lane, hc);
        const uint32_t* E2[3];
#pragma unroll
        for (int k = 0; k < 3; k++) {
            const int i = min(t2 + 256 * k, 759), h = i / 76;
            E2[k] = reinterpret_cast<const uint32_t*>(sm + CV_SM_O) + 3 + i + (h >> 1) * 360 + (h & 1) * 52;
        }
        mbar_wait(cnt + 48, 0);
        TSTAMP1X(11, 256);
        {
            uint32_t w[3][4];
#pragma unroll
            for (int k = 0; k < 3; k++) { w[k][0] = E2[k][0]; w[k][1] = E2[k][1]; w[k][2] = E2[k][64]; w[k][3] = E2[k][65]; }
#pragma unroll
            for (int k = 0; k < 3; k++)
                *reinterpret_cast<uint4*>(sm + CV_SM_T + min(t2 + 256 * k, 759) * 16) =
                    make_uint4(__byte_perm(w[k][1], w[k][0], 0x7610), __byte_perm(w[k][3], w[k][2], 0x7610), __byte_perm(w[k][1], 0, 0x1032), __byte_perm(w[k][3], 0, 0x1032));
        }
        asm volatile("bar.sync 1, 256;" ::: "memory");
        const uint2* Tc = reinterpret_cast<const uint2*>(sm + CV_SM_T) + 16 + 76 * (warp & 2) + 8 * (warp & 1) + g - 2 * ti;
        uint2 fa[8][2], fn[8][2];
        auto near_taps = [&](uint2 (&f)[8][2], int c) {
#pragma unroll
            for (int m = 0; m < 8; m++) { f[m][0] = Tc[c * (TAPB / 8) + 16 * m]; f[m][1] = Tc[c * (TAPB / 8) + 16 * m - 8]; }
        };
        near_taps(fa, 3 * wgu);
        near_taps(fn, 2 - wgu);
        TSTAMP1X(12, 256); CST(0);
        uint32_t ya = smem_u32(sm + CV_SM_Y) + wgu * 8192 + (warp & 2) * 2048 + usw(2 * lane + (warp & 1)) * 16;
        uint64_t db = make_desc(smem_u32(Us + wgu * ULEN + UPADF), 16, 256, 3);
        if (wgu) asm volatile("bar.sync 6, 384;" ::: "memory");
        int c = wgu;
        auto chain = [&](const uint2 (&f)[8][2], auto&& meanwhile) {
            float acc[64];
            asm volatile("bar.sync %0, %1;" ::"r"(c ? 4 + wgu : 2), "r"(c ? 256 : 384) : "memory");
            TSTAMPC(1 + 3 * c);
            wgmma_fence();
#pragma unroll
            for (int m = 0; m < 8; m++) {
                wgmma_rs128(acc, f[m][0], f[m][1], db - (uint64_t)(2 * m), m);
                if (m == CV_HAND && c < 4) asm volatile("bar.arrive %0, 256;" ::"r"(5 - wgu) : "memory");
            }
            wgmma_commit();
            asm volatile("griddepcontrol.launch_dependents;" ::: "memory");
            TSTAMPC(2 + 3 * c); CST(13 + (c >> 1));
            meanwhile();
            wgmma_wait<0>();
            TSTAMPC(3 + 3 * c); CST(10 + (c >> 1));
            uint32_t w[16];
#pragma unroll
            for (int j = 0; j < 16; j++) w[j] = j ? pack2(acc[4 * j] + acc[4 * j - 2], acc[4 * j + 1] + acc[4 * j - 1]) : pack2(acc[0], acc[1]);
#pragma unroll
            for (int j = 0; j < 16; j += 4) stsm_x4_t(ya + 256 * j, w[j], w[j + 1], w[j + 2], w[j + 3]);
            __syncwarp();
            if (lane == 0) mbar_arrive(cnt + 8 * c);
            c += 2; ya += 16384; db += ULEN / 4;
        };
        const uint32_t e4 = lc.e4, e8 = e4 + 428 - 4 * g;
        uint2 fl[4];
        uint32_t kk;
#pragma unroll 1
        for (;;) {
            if (c != 1) chain(fa, [&] {
                if (c == 3 || warp + c == 12) {
#pragma unroll
                    for (int k = 0; k < 19; k++) (k < 16 ? fn[(k >> 1) & 7][k & 1] : fl[k & 3]) = make_uint2(lds1(k < 10 ? e4 + 32 * k + 16 : e8 + 32 * k - 304), lds1(k < 10 ? e4 + 32 * k : e8 + 32 * k - 320));
                    fl[3] = make_uint2(lds1(lc.en), lds1(lc.en - 64));
                    kk = lds1(smem_u32(sm + CV_SM_O) + 2048 * hc + 1672);
                }
            });
            if (c > 4) break;
            if (c == 2) asm volatile("bar.sync 7, 384;" ::: "memory");
            chain(fn, [&] { if (c == 2) near_taps(fa, 4); });
        }
        TSTAMP1X(6, 256); CST(2);
        if (wgu || warp == 8) {
            constexpr int seq[29] = {5, 6, 32, 7, 33, 8, 34, 9, 35, 10, 36, 11, 12, 13, 14, 15, 16, 17, 37, 18, 38, 19, 20, 21, 39, 22, 40, 23, 24};
            uint2 f[20];
#pragma unroll
            for (int k = 0; k < 20; k++) f[k] = k < 16 ? fn[(k >> 1) & 7][k & 1] : fl[k & 3];
            far(Int<10>(), seq, lc, hc, lane, f, kk);
        }
    } else {
        asm volatile("setmaxnreg.dec.sync.aligned.u32 88;");
        CV_IDX
        const uint4* ppv = piv + tid;
        const float4* psv = sum + tid;
        const uint2* pxv = reinterpret_cast<const uint2*>(x1T + (size_t)d0 * XCP) + (tid >> 4) * 32 + (tid & 15);
        asm volatile("st.shared.u64 [%0], %1;" ::"r"(smem_u32(Xs) + tid * 16), "l"((uint64_t)ppv ^ (uint64_t)psv ^ (uint64_t)pxv) : "memory");
        const int tc = (0x04302100 >> (4 * warp)) & 7;
        const Lc lc = lane_consts(lane, tc);
        pdl_sync();
        SPAN(3 + 4 * layer, 1);
        TSTAMP(0); CST(0);
        if (tid == 0) TSTAMPC(0);
        if (threadIdx.x == 0) { GSTAMP(g_tim, 15); }
        float4 sv[4];
#pragma unroll
        for (int k = 0; k < 4; k++)
            asm volatile("ld.relaxed.gpu.global.v4.f32 {%0,%1,%2,%3}, [%4];" : "=f"(sv[k].x), "=f"(sv[k].y), "=f"(sv[k].z), "=f"(sv[k].w) : "l"(psv + 256 * k) : "memory");
        uint4 pv;
        asm volatile("ld.relaxed.gpu.global.v4.u32 {%0,%1,%2,%3}, [%4];" : "=r"(pv.x), "=r"(pv.y), "=r"(pv.z), "=r"(pv.w) : "l"(ppv) : "memory");
        uint2 xe[CV_CPB], xo[CV_CPB];
#pragma unroll
        for (int c = 0; c < CV_CPB; c++) {
            asm volatile("ld.relaxed.gpu.global.v2.u32 {%0,%1}, [%2];" : "=r"(xe[c].x), "=r"(xe[c].y) : "l"(pxv + c * (XCP / 4)) : "memory");
            asm volatile("ld.relaxed.gpu.global.v2.u32 {%0,%1}, [%2];" : "=r"(xo[c].x), "=r"(xo[c].y) : "l"(pxv + c * (XCP / 4) + 16) : "memory");
        }
        constexpr float idm = 1.0f / DM;
        uint32_t mw[4];
        float rs[8];
#pragma unroll
        for (int k = 0; k < 4; k++) {
            const uint32_t pw = k == 0 ? pv.x : k == 1 ? pv.y : k == 2 ? pv.z : pv.w;
            const float d0_ = sv[k].x * idm, d1_ = sv[k].z * idm;
            mw[k] = pack2(__uint_as_float(pw << 16) + d0_, __uint_as_float(pw & 0xffff0000u) + d1_);
            const uint32_t vr = pack2(fmaxf(fmaf(-d0_, d0_, sv[k].y * idm), 0.f), fmaxf(fmaf(-d1_, d1_, sv[k].w * idm), 0.f));
            const uint32_t ve = pack2(__uint_as_float(vr << 16) + 1e-5f, __uint_as_float(vr & 0xffff0000u) + 1e-5f);
            const uint32_t sd = pack2(sqrt_apx(__uint_as_float(ve << 16)), sqrt_apx(__uint_as_float(ve & 0xffff0000u)));
            rs[2 * k] = rcp_apx(__uint_as_float(sd << 16)); rs[2 * k + 1] = rcp_apx(__uint_as_float(sd & 0xffff0000u));
        }
        if (rs[0] != 123.f) TSTAMP(13);
        const uint32_t ua = smem_u32(Us) + usw(tid + UPADF / 8) * 16;
        uint32_t uw[CV_CPB][4];
#pragma unroll
        for (int c = 0; c < CV_CPB; c++) {
            const uint32_t e0 = sub2(xe[c].x, mw[0]), e1 = sub2(xe[c].y, mw[1]), o0 = sub2(xo[c].x, mw[2]), o1 = sub2(xo[c].y, mw[3]);
            uw[c][0] = pack2(__uint_as_float(e0 << 16) * rs[0], __uint_as_float(o0 << 16) * rs[4]); uw[c][1] = pack2(__uint_as_float(e0 & 0xffff0000u) * rs[1], __uint_as_float(o0 & 0xffff0000u) * rs[5]);
            uw[c][2] = pack2(__uint_as_float(e1 << 16) * rs[2], __uint_as_float(o1 << 16) * rs[6]); uw[c][3] = pack2(__uint_as_float(e1 & 0xffff0000u) * rs[3], __uint_as_float(o1 & 0xffff0000u) * rs[7]);
            asm volatile("st.shared.v4.u32 [%0], {%1,%2,%3,%4};" ::"r"(ua + c * ULEN * 2), "r"(uw[c][0]), "r"(uw[c][1]), "r"(uw[c][2]), "r"(uw[c][3]) : "memory");
            if (c < 2) {
                fence_async_smem();
                asm volatile("bar.arrive %0, 384;" ::"r"(2 + 4 * c) : "memory");
                if (layer > 29 - c) __trap();
            }
        }
        fence_async_smem();
#pragma unroll
        for (int c = 0; c < CV_CPB; c++) *reinterpret_cast<uint4*>(Xs + c * XLEN + tid * 8) = make_uint4(xe[c].x, xe[c].y, xo[c].x, xo[c].y);
        asm volatile("bar.arrive 7, 384;" ::: "memory");
        asm volatile("bar.sync 3, 512;" ::: "memory");
        TSTAMP(1); CST(1);
        {
            auto box = [&](auto c0, auto c1, int chunk, int cb, bool full) {
                const uint32_t ea = smem_u32(Us + cb * ULEN) + usw(chunk + UPADF / 8 + (lane ? 1 : -1)) * 16, bx = smem_u32(sm + CV_SM_B + cb * BX_LEN) + chunk * 16;
                uint32_t lo[CV_CPB][4], hi[CV_CPB][2];
#pragma unroll
                for (int c = c0; c < c1; c++) {
                    lo[c][0] = 0;
#pragma unroll
                    for (int k = 1; k < 4; k++) lo[c][k] = __shfl_up_sync(~0u, uw[c][k], 1);
#pragma unroll
                    for (int k = 0; k < 2; k++) hi[c][k] = __shfl_down_sync(~0u, uw[c][k], 1);
                }
#pragma unroll
                for (int c = c0; c < c1; c++)
                    asm volatile("{\n.reg .pred p, q;\nsetp.eq.s32 p, %7, 0;\nsetp.eq.s32 q, %7, 31;\n@p ld.shared.v4.u32 {%0,%1,%2,%3}, [%6];\n@q ld.shared.v2.u32 {%4,%5}, [%6];\n}"
                                 : "+r"(lo[c][0]), "+r"(lo[c][1]), "+r"(lo[c][2]), "+r"(lo[c][3]), "+r"(hi[c][0]), "+r"(hi[c][1]) : "r"(ea + c * ULEN * 2), "r"(lane) : "memory");
#pragma unroll
                for (int c = c0; c < c1; c++) {
                    const uint32_t e[9] = {lo[c][1], lo[c][2], lo[c][3], uw[c][0], uw[c][1], uw[c][2], uw[c][3], hi[c][0], hi[c][1]};
                    uint32_t o[8], p[8], t[7], b3[5], b5[7];
#pragma unroll
                    for (int i = 0; i < 8; i++) { o[i] = __byte_perm(e[i], e[i + 1], 0x5432); p[i] = add2(e[i], o[i]); }
#pragma unroll
                    for (int i = 0; i < 5; i++) b3[i] = add2(o[i], p[i + 1]);
                    sts4(bx + c * BX_LEN + BX_3 + 160, b3);
#pragma unroll
                    for (int i = 1; i < 7; i++) { t[i] = add2(p[i], p[i + 1]); b5[i] = add2(t[i], e[i + 2]); }
                    sts4(bx + c * BX_LEN + BX_5 + 160, b5 + 2);
                    if (full) {
#pragma unroll
                        for (int i = 1; i < 5; i++) { b3[i] = add2(b3[i], t[i + 2]); t[i] = add2(t[i], b5[i + 2]); }
                        sts4(bx + c * BX_LEN + BX_7 + 272, b3 + 1);
                        sts4(bx + c * BX_LEN + BX_9 + 272, t + 1);
                    }
                }
            };
            auto reload = [&](int c, uint32_t a) { const uint4 v = lds4(a); uw[c][0] = v.x; uw[c][1] = v.y; uw[c][2] = v.z; uw[c][3] = v.w; };
            if (warp >= 6) {
#pragma unroll
                for (int c = 0; c < 3; c++) reload(c, ua - 1024 + (c + 2) * ULEN * 2);
            }
            if (warp >= 4) {
#pragma unroll
                for (int c = 3; c < 5; c++) reload(c, ua - 2048 + c * ULEN * 2);
            }
            box(Int<0>(), Int<3>(), warp < 6 ? tid : tid - 64, warp < 6 ? 0 : 2, warp < 4);
            if (warp >= 4) box(Int<3>(), Int<5>(), tid - 128, 0, true);
            else if (tid >= 128 - CV_CPB) {
                const int c = 127 - tid;
                const uint2 v = *reinterpret_cast<const uint2*>(Us + c * ULEN + UPADF);
                const float s1 = __uint_as_float(v.x << 16), s2 = s1 + __uint_as_float(v.x & 0xffff0000u), s3 = s2 + __uint_as_float(v.y << 16), s4 = s3 + __uint_as_float(v.y & 0xffff0000u);
                unsigned char* bc = sm + CV_SM_B + c * BX_LEN;
                *reinterpret_cast<uint32_t*>(bc + BX_5 + 156) = pack2(s1, s2);
                *reinterpret_cast<uint2*>(bc + BX_7 + 264) = make_uint2(v.x << 16, pack2(s2, s3));
                *reinterpret_cast<uint2*>(bc + BX_9 + 264) = make_uint2(pack2(s1, s2), pack2(s3, s4));
            }
        }
        __syncwarp();
        if (lane == 0) mbar_arrive(cnt + 40);
        TSTAMP(2); CST(2);
        if (layer && blockIdx.x == 0 && tid == 224) g_epoch = ld_epoch();
        __syncwarp();
        if ((0x6e >> warp) & 1) {
            constexpr int seq[16] = {0, 1, 2, 3, 4, 5, 6, 32, 7, 8, 9, 33, 10, 34, 11, 12};
            uint2 f[20];
            mbar_wait(cnt, 0);
            const uint32_t e8 = lc.e4 + 428 - (lane & 28);
#pragma unroll
            for (int k = 0; k < 13; k++) f[k] = make_uint2(lds1(k < 10 ? lc.e4 + 32 * k + 16 : e8 + 32 * k - 304), lds1(k < 10 ? lc.e4 + 32 * k : e8 + 32 * k - 320));
            f[19] = make_uint2(lds1(lc.en), lds1(lc.en - 64));
            far(Int<4>(), seq, lc, tc, lane, f, lds1(smem_u32(sm + CV_SM_O) + 2048 * tc + 1672));
        }
    }
    {
        CV_IDX
        if ((0xc91 >> warp) & 1) {
            const int c = __popc(0xc91 & ((1 << warp) - 1));
            uint4 xv[2], yv[2];
#pragma unroll
            for (int k = 0; k < 2; k++) xv[k] = lds4(smem_u32(Xs + c * XLEN) + 512 * k + lane * 16);
            const uint32_t u0 = lds1(smem_u32(Us + c * ULEN) + (lane == 31 ? UPADF * 2 : 0));
            mbar_wait(cnt + 8 * c, 0);
#pragma unroll
            for (int k = 0; k < 2; k++) yv[k] = lds4(smem_u32(sm + CV_SM_Y) + c * 8192 + 512 * k + usw(lane) * 16);
            const uint4 yz = lds4(smem_u32(sm + CV_SM_Y) + c * 8192 + 4096 + usw(lane) * 16);
            const float kk = __uint_as_float(lds1(smem_u32(sm + CV_SM_O) + 2048 * c + 1272) << 16);
            yv[1].x = add2(yv[1].x, yz.x); yv[1].y = add2(yv[1].y, yz.y); yv[1].z = add2(yv[1].z, yz.z);
            yv[1].w = pack2(fmaf(kk, __uint_as_float(u0 << 16), __uint_as_float(yv[1].w << 16) + __uint_as_float(yz.w << 16)),
                            fmaf(kk, __uint_as_float(u0 << 16) + __uint_as_float(u0 & 0xffff0000u), __uint_as_float(yv[1].w & 0xffff0000u) + __uint_as_float(yz.w & 0xffff0000u)));
#pragma unroll
            for (int k = 0; k < 2; k++) cv_store(dq + c * XCP * 2 + (lane >> 4) * 256 + (lane & 15) * 8 + 512 * k, xv[k], yv[k]);
        }
        TSTAMP(4); CST(8);
        if (layer == 1) {
            const int mb = blockIdx.x >> 3, cg = blockIdx.x & 7;
            const bf16* src = dst + (size_t)(cg * 80 + (tid >> 4)) * XCP + mb * 128 + (tid & 15) * 8;
            uint32_t v[3][4];
            __syncthreads();
            uint32_t todo = warp < 8 ? 7 : 3;
#pragma unroll 1
            for (int it = 0; it < SPIN_MAX; it++) {
#pragma unroll
                for (int k = 0; k < 3; k++)
                    if (todo >> k & 1)
                        asm volatile("ld.relaxed.gpu.global.v4.u32 {%0,%1,%2,%3}, [%4];" : "=r"(v[k][0]), "=r"(v[k][1]), "=r"(v[k][2]), "=r"(v[k][3]) : "l"(src + k * (32 * XCP)) : "memory");
#pragma unroll
                for (int k = 0; k < 3; k++)
                    if ((todo >> k & 1) && v[k][0] != ~0u && v[k][1] != ~0u && v[k][2] != ~0u && v[k][3] != ~0u) {
                        *reinterpret_cast<uint4*>(sm + (32 * k + (tid >> 4)) * 272 + (tid & 15) * 16) = make_uint4(v[k][0], v[k][1], v[k][2], v[k][3]);
                        todo ^= 1u << k;
                    }
                if (!todo) break;
                __nanosleep(CV_SLEEP);
            }
            __syncthreads();
            uint32_t w[12];
#pragma unroll
            for (int k = 0; k < 3; k++) ldsm_x4(&w[4 * k], smem_u32(sm) + min(32 * k + lane, 79) * 272 + warp * 16);
            const uint32_t ot = smem_u32(sm + CV_SM_O) + warp * 1280, oa = ot + (lane & 7) * 160 + (lane >> 3) * 16;
            stsm_x4_t(oa, w[0], w[1], w[2], w[3]);
            stsm_x4_t(oa + 64, w[4], w[5], w[6], w[7]);
            asm volatile("stmatrix.sync.aligned.m8n8.x2.trans.shared.b16 [%0], {%1,%2};" ::"r"(oa + 128), "r"(w[8]), "r"(w[9]) : "memory");
            fence_async_smem();
            __syncwarp();
            if (lane == 0) {
                asm volatile("cp.async.bulk.tensor.3d.global.shared::cta.bulk_group [%0, {%1, %2, %3}], [%4];" ::"l"(&tmOut), "r"(cg * 80), "r"(mb * 64 + 8 * (warp & 7)), "r"(warp >> 3), "r"(ot) : "memory");
                asm volatile("cp.async.bulk.commit_group;" ::: "memory");
                asm volatile("cp.async.bulk.wait_group.read 0;" ::: "memory");
            }
        }
    }
    TSTAMP(3); CST(9); CST_END;
    GSTAMP(g_tim, 14);
    SPAN(3 + 4 * layer, 3);
}

template <int TA, int TB>
__device__ __forceinline__ void wgmma_n240(float (&d)[120], uint64_t da, uint64_t db, int acc) {
    asm volatile("{\n.reg .pred p;\nsetp.ne.b32 p, %124, 0;\nwgmma.mma_async.sync.aligned.m64n240k16.f32.bf16.bf16 {%0,%1,%2,%3,%4,%5,%6,%7,%8,%9,%10,%11,%12,%13,%14,%15,%16,%17,%18,%19,%20,%21,%22,%23,%24,%25,%26,%27,%28,%29,%30,%31,%32,%33,%34,%35,%36,%37,%38,%39,%40,%41,%42,%43,%44,%45,%46,%47,%48,%49,%50,%51,%52,%53,%54,%55,%56,%57,%58,%59,%60,%61,%62,%63,%64,%65,%66,%67,%68,%69,%70,%71,%72,%73,%74,%75,%76,%77,%78,%79,%80,%81,%82,%83,%84,%85,%86,%87,%88,%89,%90,%91,%92,%93,%94,%95,%96,%97,%98,%99,%100,%101,%102,%103,%104,%105,%106,%107,%108,%109,%110,%111,%112,%113,%114,%115,%116,%117,%118,%119}, %120, %121, p, 1, 1, %122, %123;\n}"
                 : "+f"(d[0]), "+f"(d[1]), "+f"(d[2]), "+f"(d[3]), "+f"(d[4]), "+f"(d[5]), "+f"(d[6]), "+f"(d[7]), "+f"(d[8]), "+f"(d[9]), "+f"(d[10]), "+f"(d[11]), "+f"(d[12]), "+f"(d[13]), "+f"(d[14]), "+f"(d[15]), "+f"(d[16]), "+f"(d[17]), "+f"(d[18]), "+f"(d[19]), "+f"(d[20]), "+f"(d[21]), "+f"(d[22]), "+f"(d[23]), "+f"(d[24]), "+f"(d[25]), "+f"(d[26]), "+f"(d[27]), "+f"(d[28]), "+f"(d[29]), "+f"(d[30]), "+f"(d[31]), "+f"(d[32]), "+f"(d[33]), "+f"(d[34]), "+f"(d[35]), "+f"(d[36]), "+f"(d[37]), "+f"(d[38]), "+f"(d[39]), "+f"(d[40]), "+f"(d[41]), "+f"(d[42]), "+f"(d[43]), "+f"(d[44]), "+f"(d[45]), "+f"(d[46]), "+f"(d[47]), "+f"(d[48]), "+f"(d[49]), "+f"(d[50]), "+f"(d[51]), "+f"(d[52]), "+f"(d[53]), "+f"(d[54]), "+f"(d[55]), "+f"(d[56]), "+f"(d[57]), "+f"(d[58]), "+f"(d[59]), "+f"(d[60]), "+f"(d[61]), "+f"(d[62]), "+f"(d[63]), "+f"(d[64]), "+f"(d[65]), "+f"(d[66]), "+f"(d[67]), "+f"(d[68]), "+f"(d[69]), "+f"(d[70]), "+f"(d[71]), "+f"(d[72]), "+f"(d[73]), "+f"(d[74]), "+f"(d[75]), "+f"(d[76]), "+f"(d[77]), "+f"(d[78]), "+f"(d[79]), "+f"(d[80]), "+f"(d[81]), "+f"(d[82]), "+f"(d[83]), "+f"(d[84]), "+f"(d[85]), "+f"(d[86]), "+f"(d[87]), "+f"(d[88]), "+f"(d[89]), "+f"(d[90]), "+f"(d[91]), "+f"(d[92]), "+f"(d[93]), "+f"(d[94]), "+f"(d[95]), "+f"(d[96]), "+f"(d[97]), "+f"(d[98]), "+f"(d[99]), "+f"(d[100]), "+f"(d[101]), "+f"(d[102]), "+f"(d[103]), "+f"(d[104]), "+f"(d[105]), "+f"(d[106]), "+f"(d[107]), "+f"(d[108]), "+f"(d[109]), "+f"(d[110]), "+f"(d[111]), "+f"(d[112]), "+f"(d[113]), "+f"(d[114]), "+f"(d[115]), "+f"(d[116]), "+f"(d[117]), "+f"(d[118]), "+f"(d[119])
                 : "l"(da), "l"(db), "n"(TA), "n"(TB), "r"(acc));
}

__device__ __forceinline__ void wgmma_n80(float (&d)[40], uint64_t da, uint64_t db, int acc) {
    asm volatile("{\n.reg .pred p;\nsetp.ne.b32 p, %42, 0;\nwgmma.mma_async.sync.aligned.m64n80k16.f32.bf16.bf16 {%0,%1,%2,%3,%4,%5,%6,%7,%8,%9,%10,%11,%12,%13,%14,%15,%16,%17,%18,%19,%20,%21,%22,%23,%24,%25,%26,%27,%28,%29,%30,%31,%32,%33,%34,%35,%36,%37,%38,%39}, %40, %41, p, 1, 1, 0, 1;\n}"
                 : "+f"(d[0]), "+f"(d[1]), "+f"(d[2]), "+f"(d[3]), "+f"(d[4]), "+f"(d[5]), "+f"(d[6]), "+f"(d[7]), "+f"(d[8]), "+f"(d[9]), "+f"(d[10]), "+f"(d[11]), "+f"(d[12]), "+f"(d[13]), "+f"(d[14]), "+f"(d[15]), "+f"(d[16]), "+f"(d[17]), "+f"(d[18]), "+f"(d[19]), "+f"(d[20]), "+f"(d[21]), "+f"(d[22]), "+f"(d[23]), "+f"(d[24]), "+f"(d[25]), "+f"(d[26]), "+f"(d[27]), "+f"(d[28]), "+f"(d[29]), "+f"(d[30]), "+f"(d[31]), "+f"(d[32]), "+f"(d[33]), "+f"(d[34]), "+f"(d[35]), "+f"(d[36]), "+f"(d[37]), "+f"(d[38]), "+f"(d[39])
                 : "l"(da), "l"(db), "r"(acc));
}

constexpr int A1_THREADS = 384;
constexpr int A1_NST = 4;
#define A1_SKEW 8
constexpr int A1_STAGE = 16384 + WQ_STAGE;
constexpr int A1_KVP = 336;
constexpr int A1_SM_KV = 2 * A1_STAGE;
constexpr int A1_SM_BAR = A1_NST * A1_STAGE;
constexpr int A1_SM_RS = A1_SM_BAR + 512;
constexpr int A1_SM_W0 = A1_SM_BAR + 3072, A1_SM_W3 = A1_SM_BAR - 3 * WOB, A1_SM_A1 = 2 * WOB, A1_SM_A0 = A1_SM_A1 + 61440;
constexpr int A1_SM_XA = A1_SM_W0 + 2 * WOB, A1_SM_XB = A1_SM_XA + 2048;
constexpr int A1_SMEM = A1_SM_W0 + 3 * WOB;
static_assert(A1_SM_W3 >= A1_SM_KV + 144 * A1_KVP && A1_SM_W3 % 512 == 0 && A1_SM_A1 % 1024 == 0 && A1_SM_A0 <= A1_SM_KV && A1_SM_A0 + 61440 <= A1_SM_W3 && A1_SMEM <= 232448, "layout");
__device__ __forceinline__ constexpr uint32_t wo_off(int h) { return h * WOB + (h < 3 ? A1_SM_W0 : h < 6 ? A1_SM_W3 - 3 * WOB : -6 * WOB); }
#define A1_FRED "red.relaxed.gpu.global.add.u32"
#define A1_FLD "ld.acquire.gpu.global.u32"
#define ST_SLEEP 20
#define ST_SLEEP0 300
#define WO_LATE bar_done
#define A1_P0 2
#define A1_PW (kb - 2)
#define A1_FSPIN SPIN_MAX
#define A1_FSLEEP 40
#define YT_LAYER 1
#define A1_WOAT 6

template <int L>
__device__ __forceinline__ void a1_mainloop(float (&acc)[120], uint32_t sbase, uint32_t bars, int wg, int tile) {
    constexpr int layer = L; (void)layer;
    const uint64_t da0 = L ? make_desc(sbase + wg * 8192, 8192, 1024, 1) : make_desc(sbase + wg * 8192, 16, 1024, 1), db0 = make_desc(sbase + 16384, 1024, 256, 3);
#pragma unroll 1
    for (int t = 0;; t++) {
        const int st = t % A1_NST;
        mbar_wait(bars + 8 * st, (t / A1_NST) & 1);
        if (t == A1_SKEW && wg == 0) mbar_wait(bars + 160, 0);
        TSTAMP3(1 + t);
        wgmma_fence();
#pragma unroll
        for (int kk = 0; kk < 4; kk++) wgmma_n240<L, 1>(acc, da0 + (uint32_t)(st * (A1_STAGE / 16) + kk * (L ? 128 : 2)), db0 + (uint32_t)(st * (A1_STAGE / 16) + (kk >> 1) * (WQ_STAGE / 32) + (kk & 1) * 32), kk ? 1 : t);
        wgmma_commit();
        if (t == 9) break;
        if (t == A1_SKEW - 1 && wg == 0) wgmma_wait<0>(); else wgmma_wait<1>();
        if (t > 0 && (threadIdx.x & 127) == 0) {
            if (t != A1_SKEW || wg) mbar_arrive(bars + 8 * (A1_NST + (t - 1) % A1_NST));
            if (t == A1_SKEW - 1 && wg == 0) mbar_arrive(bars + 8 * (A1_NST + t % A1_NST));
        }
    }
}

__global__ void __launch_bounds__(A1_THREADS, 1) a1_kernel(const int layer, const bf16* __restrict__ x0, const unsigned char* __restrict__ wq, const unsigned char* __restrict__ wo,
                                                           float2* __restrict__ rsum, uint4* __restrict__ of, const __grid_constant__ CUtensorMap tmX,
                                                           const __grid_constant__ CUtensorMap tmR, const __grid_constant__ CUtensorMap tmX1, const __grid_constant__ TileTab tab) {
    extern __shared__ __align__(1024) unsigned char stg[];
    const uint32_t sbase = smem_u32(stg);
    const uint32_t bars = sbase + A1_SM_BAR;
    const uint32_t bar_stat = bars + 64, bar_kv = bars + 72, bar_rd = bars + 168;
    const uint32_t bar_wo = bars + 208, bar_done = bars + 216, bar_pv = bars + 224, bar_kvf = bars + 232, bar_f2 = bars + 248, bar_e2 = bars + 384, que = bars + 448;
    const int tid = threadIdx.x;
    const int w = __shfl_sync(~0u, tid >> 5, 0), wg = w >> 2;
    uint32_t smid, ns;
    asm volatile("mov.u32 %0, %smid;" : "=r"(smid));
    asm volatile("mov.u32 %0, %nsmid;" : "=r"(ns));
    const auto te = tab.e[ns == tab.ns ? smid : 132 + blockIdx.x];
    const int tile = te.tile, mb = te.mb, hg = te.hg;
    float2* rst = reinterpret_cast<float2*>(stg + A1_SM_RS) + 8;
    auto issue_w = [&](int it) { bulk_load(sbase + (it % A1_NST) * A1_STAGE + 16384, wq + te.woff + it * WQ_STAGE, WQ_STAGE, bars + 8 * (it % A1_NST)); };
    auto issue_x = [&](int it, int kb) {
        asm volatile("cp.async.bulk.tensor.5d.shared::cluster.global.mbarrier::complete_tx::bytes [%0], [%1, {%3, %3, %3, %4, %5}], [%2];"
                     ::"r"(sbase + (it % A1_NST) * A1_STAGE), "l"(&tmX), "r"(bars + 8 * (it % A1_NST)), "r"(0), "r"(mb), "r"(kb) : "memory");
    };
    if (w == 8 && tile < 128) {
        const bool one = elect();
        if (one) {
#pragma unroll
            for (int i = 0; i < A1_NST; i++) mbar_init(bars + 8 * i, 1);
            asm volatile("fence.mbarrier_init.release.cluster;" ::: "memory");
        }
        __syncwarp();
        asm volatile("bar.arrive 0, 384;" ::: "memory");
        if (one) {
#define PW asm volatile("griddepcontrol.wait;" ::: "memory");
            if (layer) { issue_w(0); PW issue_x(0, te.kb0); issue_x(1, te.kb0 + 1); }
            else { issue_x(0, te.kb0); issue_x(1, te.kb0 + 1); PW issue_w(0); }
            issue_w(1);
#pragma unroll
            for (int i = 0; i < A1_NST; i++) mbar_expect_tx(bars + 8 * i, A1_STAGE);
            asm volatile("griddepcontrol.launch_dependents;" ::: "memory");
#pragma unroll
            for (int kb = 2; kb < A1_P0; kb++) { issue_x(kb, te.kb0 + kb); issue_w(kb); }
            DBGC(34); DBGV(33, smid); DBGV(40, t_entry); DBGV(30, t_a); DBGV(31, t_b); DBGV(32, t_c); DBGV(38, t_d); DBGV(39, t_e);
        }
    }
    if (tile >= 128) { sm_idle(layer); return; }
    if (wg == 2) {
        if (w != 8) {
            if (tid == 320) { prefetch_tmap(&tmX); prefetch_tmap(&tmR); prefetch_tmap(&tmX1); }
            asm volatile("bar.sync 0, 384;" ::: "memory");
        }
        if (w == 9) {
            asm volatile("bar.arrive 3, 64;" ::: "memory");
            if (layer == 0) pdl_sync();
            float4 a[2] = {};
#pragma unroll
            for (int k = 0; k < 10; k++)
#pragma unroll
                for (int h = 0; h < 2; h++) {
                    const int c4 = min(tid - 288 + 32 * h, 59);
                    const float4 v = __ldcg(reinterpret_cast<const float4*>(g_csp + k * 1920 + hg * 80) + c4 + (c4 / 20) * 140);
                    a[h].x += v.x; a[h].y += v.y; a[h].z += v.z; a[h].w += v.w;
                }
#pragma unroll
            for (int h = 0; h < 2; h++)
#pragma unroll
                for (int k = 0; k < 4; k++) {
                    const float c = 0.5f * (k == 0 ? a[h].x : k == 1 ? a[h].y : k == 2 ? a[h].z : a[h].w), c1 = c - rbf(c), c2 = c1 - rbf(c1);
                    *reinterpret_cast<uint4*>(stg + A1_SM_XB + (4 * min(tid - 288 + 32 * h, 59) + k) * 16) = make_uint4(pack2(c, c1), pack2(c2, 0.f), 0u, 0u);
                }
            fence_async_smem();
            __syncwarp();
            if (tid == 288) mbar_arrive(bar_stat);
#pragma unroll 4
            for (int k = 0; k < 40; k++) asm volatile("st.global.v4.u32 [%0], {%1,%1,%1,%1};" ::"l"(of + (mb * 8 + hg) * 1280 + 32 * k + (tid - 288)), "r"(~0u) : "memory");
            asm volatile("fence.acq_rel.gpu;" ::: "memory");
            asm volatile("fence.proxy.async.global;" ::: "memory");
            __syncwarp();
            if (tid == 288) mbar_arrive(bar_done);
            if (layer == YT_LAYER) {
#pragma unroll 4
                for (int k = tid - 288; k < 5 * XCP / 8; k += 32) asm volatile("st.global.v4.u32 [%0], {%1,%1,%1,%1};" ::"l"(reinterpret_cast<uint4*>(g_yT) + tile * (5 * XCP / 8) + k), "r"(~0u) : "memory");
            }
            TSTAMP1T(9, 288);
        } else if (w == 8) {
            asm volatile("bar.sync 3, 64;" ::: "memory");
            if (elect()) {
#pragma unroll 1
                for (int kb = A1_P0; kb < 10; kb++) {
                    if (kb < A1_NST) mbar_wait(bars + 8 * A1_PW, 0);
                    else {
                        mbar_wait(bars + 8 * (A1_NST + kb % A1_NST), ((kb / A1_NST) - 1) & 1);
                        if (layer && kb < 9) mbar_wait(bar_rd + 8 * (kb - A1_NST), 0);
                        mbar_expect_tx(bars + 8 * (kb % A1_NST), A1_STAGE);
                    }
                    issue_x(kb, kb < 5 ? kb + te.kb0 : kb - te.kb0); issue_w(kb);
                    if (kb == A1_WOAT) {
                        mbar_expect_tx(bar_wo, 8 * WOB);
                        bulk_load(sbase + A1_SM_W0, wo + hg * 8 * WOB, 2 * WOB, bar_wo);
                    }
                }
                TSTAMP1T(6, 256);
                mbar_wait(bars + 8 * (A1_NST + 3), 1);
                bulk_load(sbase + A1_SM_W3, wo + (hg * 8 + 3) * WOB, 3 * WOB, bar_wo);
            }
            __syncwarp();
        } else {
            const int j = tid - 320;
            const uint32_t tag = ld_epoch();
            if (tid == 352) sm_started(layer);
            if (layer == 0) {
                const uint4* src = reinterpret_cast<const uint4*>(x0 + (size_t)(mb * 128 + hg * 16 + (j >> 2)) * DM);
                uint4 v[20];
#pragma unroll
                for (int k = 0; k < 20; k++) v[k] = __ldg(src + (j & 3) + 4 * k);
                const float p0 = __uint_as_float(__shfl_sync(~0u, v[0].x, j & 28) << 16);
                float s[2] = {0.f, 0.f}, q[2] = {0.f, 0.f};
#pragma unroll
                for (int k = 0; k < 20; k++) {
                    const uint32_t w[4] = {v[k].x, v[k].y, v[k].z, v[k].w};
#pragma unroll
                    for (int i = 0; i < 4; i++) {
                        const float a = __uint_as_float(w[i] << 16) - p0, b = __uint_as_float(w[i] & 0xffff0000u) - p0;
                        s[0] += a; s[1] += b; q[0] = fmaf(a, a, q[0]); q[1] = fmaf(b, b, q[1]);
                    }
                }
                float s0 = s[0] + s[1], q0 = q[0] + q[1];
#pragma unroll
                for (int o = 1; o <= 2; o <<= 1) { s0 += __shfl_xor_sync(~0u, s0, o); q0 += __shfl_xor_sync(~0u, q0, o); }
                if ((j & 3) == 0) {
                    const float d = s0 * (1.0f / DM);
                    const uint32_t ms = pack2(p0 + d, sqrt_apx(rbf(rbf(fmaxf(fmaf(-d, d, q0 * (1.0f / DM)), 0.f)) + 1e-5f)));
                    asm volatile("st.global.cg.u64 [%0], %1;" ::"l"(g_rstat + mb * 128 + (j & 4) * 16 + hg * 8 + (j >> 3)), "l"(tagw(ms, tag)) : "memory");
                    g_piv[mb * 128 + hg * 16 + ((j >> 2) & 8) + (j & 4) + ((j >> 3) & 3)] = __ushort_as_bfloat16((unsigned short)ms);
                }
            }
            float o[4];
            int row;
            if (layer == 0) {
                ulonglong2 v;
#pragma unroll 1
                for (int it = 0; it < SPIN_MAX; it++) {
                    v = ld_tag2(reinterpret_cast<const ulonglong2*>(g_rstat + mb * 128) + j);
                    if (tag_ok(v, tag)) break;
                    __nanosleep(100);
                }
                o[0] = __uint_as_float((uint32_t)v.x << 16); o[1] = rcp_apx(__uint_as_float((uint32_t)v.x & 0xffff0000u));
                o[2] = __uint_as_float((uint32_t)v.y << 16); o[3] = rcp_apx(__uint_as_float((uint32_t)v.y & 0xffff0000u));
                row = 2 * j;
            } else {
                const int ch = j & 7, kg = (j >> 3) & 3;
                const unsigned char* src = stg + (j >> 5) * 8192 + (hg & 3) * 2048;
                float s[8], q[8], p0[8];
#pragma unroll
                for (int i = 0; i < 8; i++) { s[i] = 0.f; q[i] = 0.f; }
#pragma unroll 1
                for (int it = 0; it < 5; it++) {
                    uint4 v[4];
                    mbar_wait(bars + 8 * (it % A1_NST), it / A1_NST);
#pragma unroll
                    for (int k = 0; k < 4; k++) v[k] = *reinterpret_cast<const uint4*>(src + (it % A1_NST) * A1_STAGE + (4 * k + kg) * 128 + ((ch ^ ((4 * k + kg) & 7)) << 4));
                    if (it == 0) {
                        const uint4 pv = *reinterpret_cast<const uint4*>(src + (ch << 4));
                        const uint32_t w[4] = {pv.x, pv.y, pv.z, pv.w};
#pragma unroll
                        for (int i = 0; i < 4; i++) { p0[2 * i] = __uint_as_float(w[i] << 16); p0[2 * i + 1] = __uint_as_float(w[i] & 0xffff0000u); }
                    }
                    asm volatile("" :: "r"(v[0].x), "r"(v[1].x), "r"(v[2].x), "r"(v[3].x), "f"(p0[0]) : "memory");
                    __syncwarp();
                    if ((tid & 31) == 0) mbar_arrive(bar_rd + 8 * it);
#pragma unroll
                    for (int k = 0; k < 4; k++) {
                        const uint32_t w[4] = {v[k].x, v[k].y, v[k].z, v[k].w};
#pragma unroll
                        for (int i = 0; i < 4; i++) {
                            const float a = __uint_as_float(w[i] << 16) - p0[2 * i], b = __uint_as_float(w[i] & 0xffff0000u) - p0[2 * i + 1];
                            s[2 * i] += a; s[2 * i + 1] += b; q[2 * i] = fmaf(a, a, q[2 * i]); q[2 * i + 1] = fmaf(b, b, q[2 * i + 1]);
                        }
                    }
                }
#pragma unroll
                for (int i = 0; i < 4; i++) {
                    const bool up = kg & 2;
                    const float ss = __shfl_xor_sync(~0u, up ? s[i] : s[i + 4], 16), qq = __shfl_xor_sync(~0u, up ? q[i] : q[i + 4], 16);
                    s[i] = (up ? s[i + 4] : s[i]) + ss; q[i] = (up ? q[i + 4] : q[i]) + qq; p0[i] = up ? p0[i + 4] : p0[i];
                }
#pragma unroll
                for (int i = 0; i < 2; i++) {
                    const bool up = kg & 1;
                    const float ss = __shfl_xor_sync(~0u, up ? s[i] : s[i + 2], 8), qq = __shfl_xor_sync(~0u, up ? q[i] : q[i + 2], 8);
                    s[i] = (up ? s[i + 2] : s[i]) + ss; q[i] = (up ? q[i + 2] : q[i]) + qq; p0[i] = up ? p0[i + 2] : p0[i];
                }
                uint4* gp = g_halo + 86016 + mb * 512 + j;
                const float d0 = s[0] * (1.0f / 80.0f), d1 = s[1] * (1.0f / 80.0f);
                asm volatile("st.relaxed.gpu.global.v4.f32 [%0], {%1,%2,%3,%4};" ::"l"(gp + hg * 64), "f"(p0[0] + d0), "f"(fmaxf(fmaf(-d0, s[0], q[0]), 0.f)), "f"(p0[1] + d1), "f"(fmaxf(fmaf(-d1, s[1], q[1]), 0.f)) : "memory");
                __nanosleep(ST_SLEEP0);
                uint32_t pw[8][4], todo = 0xff;
#pragma unroll 1
                for (int it = 0; it < SPIN_MAX; it++) {
#pragma unroll
                    for (int k = 0; k < 8; k++)
                        if (todo >> k & 1) asm volatile("ld.relaxed.gpu.global.v4.u32 {%0,%1,%2,%3}, [%4];" : "=r"(pw[k][0]), "=r"(pw[k][1]), "=r"(pw[k][2]), "=r"(pw[k][3]) : "l"(gp + k * 64) : "memory");
#pragma unroll
                    for (int k = 0; k < 8; k++)
                        if (__all_sync(~0u, pw[k][0] != ~0u && pw[k][1] != ~0u && pw[k][2] != ~0u && pw[k][3] != ~0u)) todo &= ~(1u << k);
                    if (!todo) break;
                    __nanosleep(ST_SLEEP);
                }
#pragma unroll
                for (int r = 0; r < 2; r++) {
                    float mean = 0.f, m2 = 0.f;
#pragma unroll
                    for (int k = 0; k < 8; k++) mean += __uint_as_float(pw[k][2 * r]);
                    mean *= 0.125f;
#pragma unroll
                    for (int k = 0; k < 8; k++) {
                        const float dm = __uint_as_float(pw[k][2 * r]) - mean;
                        m2 += fmaf(80.0f * dm, dm, __uint_as_float(pw[k][2 * r + 1]));
                    }
                    o[2 * r] = rbf(mean);
                    o[2 * r + 1] = rcp_apx(rbf(sqrt_apx(rbf(rbf(m2 * (1.0f / DM)) + 1e-5f))));
                }
                row = (j >> 5) * 64 + (j & 7) * 8 + ((j >> 3) & 3) * 2;
                if (hg == 0) *reinterpret_cast<uint32_t*>(g_piv + SEQ + mb * 128 + 2 * (row & 60) + 4 * (row >> 6) + (row & 3)) = __byte_perm(__float_as_uint(o[0]), __float_as_uint(o[2]), 0x7632);
            }
#pragma unroll
            for (int r = 0; r < 2; r++)
                *reinterpret_cast<uint4*>(stg + A1_SM_XA + (row + r) * 16) = make_uint4(__byte_perm(__float_as_uint(-o[2 * r]), 0, 0x3232), __float_as_uint(-o[2 * r]) >> 16, 0u, 0u);
            *reinterpret_cast<float4*>(rst + row + (row >> 6) * 8) = make_float4(o[0], o[1], o[2], o[3]);
            fence_async_smem();
            TSTAMP1T(7, 320);
            if (tid == 320) DBGC(44);
            __syncwarp();
            if ((tid & 31) == 0) mbar_arrive(bar_stat);
        }
        if (tid == 320) DBGCAL(0);
        if (tid == 352) {
            mbar_wait(WO_LATE, 0);
            mbar_wait(bar_done, 0);
            bulk_load(sbase, wo + (hg * 8 + 6) * WOB, 2 * WOB, bar_wo);
            bulk_load(sbase + A1_SM_W0 + 2 * WOB, wo + (hg * 8 + 2) * WOB, WOB, bar_wo);
        }
        if (w < 10) {
            const int cw = w - 8;
            const uint32_t* fl = reinterpret_cast<const uint32_t*>(rsum + 2 * SEQ) + (((layer * 16 + mb) * 2 + cw) * 8 + (tid & 7)) * FSTR;
            const unsigned char* src = reinterpret_cast<const unsigned char*>(of) + mb * 163840 + cw * 10240 + (tid & 7) * 20480;
            const uint32_t sl = sbase + (cw ? A1_SM_A1 : A1_SM_A0);
            mbar_wait(cw ? bar_done : bar_kvf, 0);
            if ((tid & 31) == 0) {
                mbar_expect_tx(bar_f2 + 64 * cw + 64, 10240);
                tma_load_3d(sl + 51200, &tmR, layer ? 0 : hg * 80, layer ? hg * 80 : mb * 64, layer ? mb * 2 + cw : cw, bar_f2 + 64 * cw + 64);
            }
            __syncwarp();
            uint32_t pend = 0xffu & ~(1u << hg), v = 0;
            const uint32_t bo = wo_off((tid & 7) + ((tid & 7) < hg)) >> 4, lt = (1u << (tid & 31)) - 1;
#pragma unroll 1
            for (int it = 0; pend && it < 2 * SPIN_MAX; it++) {
                if (v != 4 && (pend >> (tid & 31) & 1)) asm volatile(A1_FLD " %0, [%1];" : "=r"(v) : "l"(fl) : "memory");
                uint32_t fr;
                asm volatile("{\n.reg .pred p;\nmbarrier.test_wait.parity.shared::cta.b64 p, [%1], 0;\nselp.b32 %0, 1, 0, p;\n}" : "=r"(fr) : "r"(bar_e2 + 16 * cw + (tid & 1) * 8) : "memory");
                fr = __ballot_sync(~0u, fr);
                uint32_t m = __ballot_sync(~0u, v == 4 || it >= A1_FSPIN) & pend;
                const int q = 8 - __popc(pend) + __popc(m & lt);
                m &= __ballot_sync(~0u, q < ((fr & 2) ? 8 : (fr & 1) ? 7 : 5));
                pend ^= m;
                if (m >> (tid & 31) & 1) DBGC(12 + cw * 8 + (tid & 7));
                if (!m) __nanosleep(A1_FSLEEP);
                else asm volatile("fence.proxy.async.global;" ::: "memory");
                if (m >> (tid & 31) & 1) {
                    bulk_load(q == 7 && !cw ? sbase + A1_SM_W0 : sl + (q < 6 ? q : q - 6) * 10240, src, 10240, bar_f2 + 64 * cw + 8 * q);
                    asm volatile("st.shared.u32 [%0], %1;" ::"r"(que + 32 * cw + 4 * q), "r"(bo) : "memory");
                    mbar_expect_tx(bar_f2 + 64 * cw + 8 * q, 10240);
                    DBGC(44 + cw * 8 + q);
                }
                __syncwarp();
            }
        }
    } else {
        if (tid == 0) {
            mbar_init(bar_stat, 3);
#pragma unroll
            for (int i = 0; i < 8; i++) mbar_init(bar_kv + 8 * i, 1);
            mbar_init(bars + 144, 1);
            mbar_init(bars + 160, 1);
#pragma unroll
            for (int i = 0; i < 5; i++) mbar_init(bar_rd + 8 * i, 2);
            asm volatile("fence.mbarrier_init.release.cluster;" ::: "memory");
        } else if (tid == 32) {
            mbar_init(bar_wo, 1); mbar_init(bar_done, 3); mbar_init(bar_pv, 4); mbar_init(bar_kvf, 8);
#pragma unroll
            for (int i = 0; i < 4; i++) { mbar_init(bar_e2 + 8 * i, i == 1 ? 2 : 1); mbar_init(bars + 8 * (A1_NST + i), 2); }
            asm volatile("fence.mbarrier_init.release.cluster;" ::: "memory");
        } else if (tid == 96) {
#pragma unroll
            for (int i = 0; i < 4; i++) mbar_init(bars + 416 + 8 * i, 1);
            asm volatile("fence.mbarrier_init.release.cluster;" ::: "memory");
        } else if (tid == 64) {
#pragma unroll
            for (int i = 1; i <= 16; i++) mbar_init(bar_f2 + 8 * i, 1);
            asm volatile("fence.mbarrier_init.release.cluster;" ::: "memory");
        }
        asm volatile("bar.sync 0, 384;" ::: "memory");
        SPAN(1 + 4 * layer, 0);
        constexpr int on = 1;
        float acc[120];
        const int lane = tid & 31, warp = w & 7, g = lane >> 2, t = lane & 3;
        if (on) {
            SPAN(1 + 4 * layer, 1);
            TSTAMP1(0);
            if (threadIdx.x == 0) { GSTAMP(g_tim1, 15); }
            TSTAMP3(0);
            if (tid == 0) TSTAMP2(0);
            TSTAMP4(0);
            if (tid == 0) DBGC(60);
            if (layer == 0) a1_mainloop<0>(acc, sbase, bars, wg, tile); else a1_mainloop<1>(acc, sbase, bars, wg, tile);
            uint32_t ok;
            asm volatile("{\n.reg .pred p;\nmbarrier.test_wait.parity.shared::cta.b64 p, [%1], 0;\nselp.b32 %0, 1, 0, p;\n}" : "=r"(ok) : "r"(bar_stat) : "memory");
            if (tid == 128 && !ok) mbar_arrive(bars + 160);
            __syncwarp();
            mbar_wait(bar_stat, 0);
            wgmma_fence();
            wgmma_n240<0, 0>(acc, make_desc(sbase + A1_SM_XA + wg * 1024, 0, 128, 0), make_desc(sbase + A1_SM_XB, 0, 128, 0), 1);
            wgmma_commit();
            if (tid == 128 && ok) mbar_arrive(bars + 160);
            mbar_wait(bars + 8 * (A1_NST + 3), 1);
        }
        const float2* rw = rst + 16 * warp + 8 * wg;
        const float rb0 = rw[g + 8].y, ra = rw[g].y * 0.22360679774997896f, rb = rb0 * 0.22360679774997896f;
        wgmma_wait<0>();
        if ((tid & 127) == 0) mbar_arrive(bar_done);
        TSTAMP1(2);
        TSTAMP1T(13, 224);
        if ((tid & 127) == 0) DBGC(62 - wg);
        uint32_t f[2][30];
#pragma unroll
        for (int j = 10; j < 30; j++) f[1][j] = pack2(acc[4 * j + 2], acc[4 * j + 3]);
        if ((warp & 3) == 3) {
            uint4* hout = g_halo + (((layer * 16 + mb) * 8 + hg) * 2 + wg) * 168;
#pragma unroll
            for (int j = 0; j < 20; j += 4)
                asm volatile("st.relaxed.gpu.global.v4.u32 [%0], {%1,%2,%3,%4};" ::"l"(hout + 8 * j + lane), "r"(f[1][10 + j]), "r"(f[1][11 + j]), "r"(f[1][12 + j]), "r"(f[1][13 + j]) : "memory");
            if (t == 0) asm volatile("st.relaxed.gpu.global.f32 [%0], %1;" ::"l"(reinterpret_cast<float*>(hout + 160) + g), "f"(rb0) : "memory");
        }
        TSTAMP1T(12, 224);
        const uint32_t kvw = sbase + A1_SM_KV + (16 * warp + 8 * wg) * A1_KVP;
        const uint32_t mrow = kvw + (lane & 7) * A1_KVP + (lane >> 3) * 16;
#pragma unroll
        for (int j = 0; j < 20; j += 4) stsm_x4(mrow + 16 * A1_KVP + 16 * j, f[1][10 + j], f[1][11 + j], f[1][12 + j], f[1][13 + j]);
        __syncwarp();
        if (lane == 0 && (warp & 3) != 3) mbar_arrive(bar_kv + 8 * (warp + 1));
#pragma unroll
        for (int j = 0; j < 30; j++) f[0][j] = pack2(acc[4 * j], acc[4 * j + 1]);
        stsm_x4(mrow + 8 * A1_KVP + 160, f[0][20], f[0][21], f[0][22], f[0][23]);
        stsm_x4(mrow + 8 * A1_KVP + 224, f[0][24], f[0][25], f[0][26], f[0][27]);
        asm volatile("stmatrix.sync.aligned.m8n8.x2.shared.b16 [%0], {%1,%2};" ::"r"(mrow + 8 * A1_KVP + 288), "r"(f[0][28]), "r"(f[0][29]) : "memory");
#pragma unroll
        for (int j = 0; j < 10; j++) f[1][j] = pack2(acc[4 * j + 2], acc[4 * j + 3]);
        __syncwarp();
        uint32_t vb[10][2], vp[12], kp[12];
#pragma unroll
        for (int j = 0; j < 10; j += 2) ldsm_x4_t(&vb[j][0], kvw + (8 + (lane & 15)) * A1_KVP + 160 + (lane >> 4) * 16 + 16 * j);
        const bool up0 = 2 * t > g, up1 = 2 * t + 1 > g, edge = (mb | (warp & 3)) == 0;
        float rk[4];
        auto above = [&]() {
            mbar_wait(bar_kv + 8 * warp, 0);
#pragma unroll
            for (int j = 0; j < 12; j += 4) ldsm_x4(&kp[j], mrow + 16 * j);
            rk[0] = rw[2 * t - (up0 ? 8 : 0)].y; rk[1] = rw[2 * t + 1 - (up1 ? 8 : 0)].y;
#pragma unroll
            for (int j = 0; j < 12; j += 4) ldsm_x4_t(&vp[j], mrow + 160 + 16 * j - (j == 8 ? (lane & 16) * 2 : 0));
            __syncwarp();
            if (lane == 0) mbar_arrive(bar_kvf);
        };
        auto halo = [&]() {
            if (lane == 0) mbar_arrive(bar_kvf);
            const uint4* hin = g_halo + (((layer * 16 + mb - 1) * 8 + hg) * 2 + wg) * 168;
            uint32_t hv[22] = {};
            rk[0] = rw[2 * t].y; rk[1] = rw[2 * t + 1].y;
            if (mb > 0) {
#pragma unroll 1
                for (int it = 0; it < SPIN_MAX; it++) {
#pragma unroll
                    for (int k = 0; k < 20; k += 4)
                        asm volatile("ld.relaxed.gpu.global.v4.u32 {%0,%1,%2,%3}, [%4];" : "=r"(hv[k]), "=r"(hv[k + 1]), "=r"(hv[k + 2]), "=r"(hv[k + 3]) : "l"(hin + 8 * k + lane) : "memory");
                    asm volatile("ld.relaxed.gpu.global.v2.u32 {%0,%1}, [%2];" : "=r"(hv[20]), "=r"(hv[21]) : "l"(reinterpret_cast<const uint2*>(hin + 160) + t) : "memory");
                    uint32_t m = max(hv[20], hv[21]);
#pragma unroll
                    for (int k = 0; k < 20; k += 2) m = __vimax3_u32(m, hv[k], hv[k + 1]);
                    if (!__any_sync(~0u, m == ~0u)) break;
                }
            }
            if (tid == 0) mbar_arrive(bars + 144);
            if (lane == 0) DBGC(52 - 16 * wg);
#pragma unroll
            for (int j = 0; j < 10; j++) {
                kp[j] = hv[j];
                asm volatile("movmatrix.sync.aligned.m8n8.trans.b16 %0, %1;" : "=r"(vp[j]) : "r"(hv[10 + j]));
            }
            if (up0) rk[0] = __uint_as_float(hv[20]);
            if (up1) rk[1] = __uint_as_float(hv[21]);
        };
        rk[2] = rw[2 * t + (up0 ? 0 : 8)].y; rk[3] = rw[2 * t + 1 + (up1 ? 0 : 8)].y;
        uint32_t qs[4][2];
#pragma unroll
        for (int h = 0; h < 4; h++) {
            qs[h][0] = (t >> 1) == (h & 1) ? f[0][5 * (h >> 1) + 2] : 0u; qs[h][1] = (t >> 1) == (h & 1) ? f[1][5 * (h >> 1) + 2] : 0u;
            asm volatile("" : "+r"(qs[h][0]), "+r"(qs[h][1]));
        }
#pragma unroll
        for (int j = 0; j < 10; j++) asm volatile("" : "+r"(f[0][j]), "+r"(f[1][j]), "+r"(f[0][10 + j]));
        if (warp & 3) above(); else if (wg) halo();
        TSTAMP1T(10, 64);
        if (warp && !wg) mbar_wait(bars + 416 + 8 * warp, 0);
        float sc[4][3][4];
#pragma unroll
        for (int h = 0; h < 4; h++) {
            const int jb = 5 * (h >> 1) + 3 * (h & 1), js = 5 * (h >> 1) + 2;
#pragma unroll
            for (int nt = 1; nt < 3; nt++) {
#pragma unroll
                for (int e = 0; e < 4; e++) sc[h][nt][e] = 0.f;
                mma_bf16(sc[h][nt], f[0][jb], f[1][jb], f[0][jb + 1], f[1][jb + 1], f[nt - 1][10 + jb], f[nt - 1][11 + jb]);
                mma_bf16_k8(sc[h][nt], qs[h][0], qs[h][1], f[nt - 1][10 + js]);
            }
        }
        if (warp == 0) halo();
        TSTAMP1(8);
#pragma unroll
        for (int h = 0; h < 4; h++) {
            const int jb = 5 * (h >> 1) + 3 * (h & 1), js = 5 * (h >> 1) + 2;
#pragma unroll
            for (int e = 0; e < 4; e++) sc[h][0][e] = 0.f;
            mma_bf16(sc[h][0], f[0][jb], f[1][jb], f[0][jb + 1], f[1][jb + 1], kp[jb], kp[jb + 1]);
            mma_bf16_k8(sc[h][0], qs[h][0], qs[h][1], kp[js]);
        }
        TSTAMP1T(3, 64);
        float p[4][4], sum[4][2];
        uint32_t lg[4][2], mx[4];
        const float rl[4] = {rk[0] * ra, rk[1] * ra, rk[2] * rb, rk[3] * rb};
        auto max2 = [](uint32_t a, uint32_t b) { uint32_t r; asm("max.bf16x2 %0, %1, %2;" : "=r"(r) : "r"(a), "r"(b)); return r; };
#pragma unroll
        for (int h = 0; h < 4; h++) {
            lg[h][0] = pack2((up0 ? sc[h][0][0] : sc[h][1][0]) * rl[0], (up0 ? sc[h][1][2] : sc[h][2][2]) * rl[2]);
            lg[h][1] = pack2((up1 ? sc[h][0][1] : sc[h][1][1]) * rl[1], (up1 ? sc[h][1][3] : sc[h][2][3]) * rl[3]);
            if (edge) {
                if (up0) lg[h][0] = __byte_perm(lg[h][0], 0xce6eu, 0x3254);
                if (up1) lg[h][1] = __byte_perm(lg[h][1], 0xce6eu, 0x3254);
            }
            mx[h] = max2(lg[h][0], lg[h][1]);
        }
#pragma unroll
        for (int o = 1; o <= 2; o <<= 1)
#pragma unroll
            for (int h = 0; h < 4; h++) mx[h] = max2(mx[h], __shfl_xor_sync(~0u, mx[h], o));
#pragma unroll
        for (int h = 0; h < 4; h++)
#pragma unroll
            for (int r = 0; r < 2; r++) {
                const float m = __uint_as_float(r ? mx[h] & 0xffff0000u : mx[h] << 16);
#pragma unroll
                for (int e = 0; e < 2; e++)
                    asm("ex2.approx.ftz.f32 %0, %1;" : "=f"(p[h][2 * r + e]) : "f"((__uint_as_float(r ? lg[h][e] & 0xffff0000u : lg[h][e] << 16) - m) * 1.4426950408889634f));
                sum[h][r] = p[h][2 * r] + p[h][2 * r + 1];
            }
#pragma unroll
        for (int o = 1; o <= 2; o <<= 1)
#pragma unroll
            for (int h = 0; h < 4; h++)
#pragma unroll
                for (int r = 0; r < 2; r++) sum[h][r] += __shfl_xor_sync(~0u, sum[h][r], o);
        TSTAMP1T(5, 64);
        const uint32_t mu = (up0 ? 0xffffu : 0u) | (up1 ? 0xffff0000u : 0u);
        uint32_t ob[10][2];
#pragma unroll
        for (int P = 0; P < 2; P++) {
            float os[2][4];
#pragma unroll
            for (int e = 0; e < 2; e++) {
                const int h = 2 * P + e;
                const float i0 = rcp_apx(sum[h][0]), i1 = rcp_apx(sum[h][1]);
                const uint32_t w0 = pack2(p[h][0] * rk[0] * i0, p[h][1] * rk[1] * i0), w1 = pack2(p[h][2] * rk[2] * i1, p[h][3] * rk[3] * i1);
#pragma unroll
                for (int dt = 0; dt < 3; dt++) {
                    const int j = 5 * P + (dt < 2 ? 3 * e + dt : 2);
                    float o[4] = {0.f, 0.f, 0.f, 0.f};
                    mma_bf16(o, w0 & ~mu, w1 & mu, 0u, w1 & ~mu, vb[j][0], vb[j][1]);
                    mma_bf16_k8(o, w0 & mu, 0u, vp[j]);
                    if (dt < 2) { ob[j][0] = pack2(o[0], o[1]); ob[j][1] = pack2(o[2], o[3]); }
                    else { os[e][0] = o[0]; os[e][1] = o[1]; os[e][2] = o[2]; os[e][3] = o[3]; }
                }
            }
#pragma unroll
            for (int k = 0; k < 4; k++) os[0][k] = t < 2 ? os[0][k] : os[1][k];
            ob[5 * P + 2][0] = pack2(os[0][0], os[0][1]); ob[5 * P + 2][1] = pack2(os[0][2], os[0][3]);
        }
        const uint32_t sl = sbase + (wg ? A1_SM_A1 : A1_SM_A0);
        const uint32_t o0 = (warp & 3) * 2048 + g * 64 + ((t ^ (g >> 1)) << 4), o1 = 8192 + (warp & 3) * 512 + g * 32 + ((t ^ ((g >> 2) << 1)) << 3);
        mbar_wait(bar_done, 0);
        if (wg == 0) mbar_wait(bar_kvf, 0);
#pragma unroll
        for (int h = 0; h < 2; h++) {
            asm volatile("st.shared.v4.u32 [%0], {%1,%2,%3,%4};" ::"r"(sl + o0 + h * 1024), "r"(ob[0][h]), "r"(ob[1][h]), "r"(ob[2][h]), "r"(ob[3][h]) : "memory");
            asm volatile("st.shared.v4.u32 [%0], {%1,%2,%3,%4};" ::"r"(sl + o0 + h * 1024 + 512), "r"(ob[4][h]), "r"(ob[5][h]), "r"(ob[6][h]), "r"(ob[7][h]) : "memory");
            asm volatile("st.shared.v2.u32 [%0], {%1,%2};" ::"r"(sl + o1 + h * 256), "r"(ob[8][h]), "r"(ob[9][h]) : "memory");
        }
        if (wg && lane == 0) mbar_arrive(bars + 384 + 8 * warp);
        fence_async_smem();
        __syncwarp();
        TSTAMP1T(4, 64);
        TSTAMP1(1);
        TSTAMP2(1);
        const unsigned char* ot = reinterpret_cast<const unsigned char*>(of) + mb * 163840 + wg * 10240;
        if (lane == 0) {
            asm volatile("cp.async.bulk.global.shared::cta.bulk_group [%0], [%1], 2048;" ::"l"(ot + hg * 20480 + (warp & 3) * 2048), "r"(sl + (warp & 3) * 2048) : "memory");
            asm volatile("cp.async.bulk.global.shared::cta.bulk_group [%0], [%1], 512;" ::"l"(ot + hg * 20480 + 8192 + (warp & 3) * 512), "r"(sl + 8192 + (warp & 3) * 512) : "memory");
            asm volatile("cp.async.bulk.commit_group;" ::: "memory");
            if (wg == 0) mbar_arrive(bar_pv);
            asm volatile("cp.async.bulk.wait_group 0;" ::: "memory");
            asm volatile(A1_FRED " [%0], 1;" ::"l"(reinterpret_cast<uint32_t*>(rsum + 2 * SEQ) + (((layer * 16 + mb) * 2 + wg) * 8 + hg) * FSTR) : "memory");
            DBGC(4 + warp);
        }
        TSTAMP4(11);
        float ac2[40];
        const uint64_t db0 = make_desc(sbase, 1024, 256, 3), db1 = make_desc(sbase + 10240, 512, 256, 3), da0 = make_desc(sl, 16, 1024, 2), da1 = make_desc(sl + 8192, 16, 256, 3);
        const uint32_t o7 = wg ? 640 : (A1_SM_W0 - A1_SM_A0) >> 4;
        const uint32_t trow = ((lane & 7) + 8 * (lane >> 4)) * 128 + (((2 * (warp & 3) + ((lane >> 3) & 1)) ^ (lane & 7)) << 4);
        uint32_t xr[10][2];
        mbar_wait(bar_f2 + 64 * wg + 64, 0);
        if (layer == 0) {
#pragma unroll
            for (int j = 0; j < 10; j += 2) ldsm_x4(&xr[j][0], sl + 51200 + (16 * (warp & 3) + (lane & 15)) * 160 + (lane >> 4) * 16 + 16 * j);
        } else {
#pragma unroll
            for (int j = 0; j < 10; j += 2) ldsm_x4_t(&xr[j][0], sl + 51200 + trow + 1024 * j);
        }
        const uint32_t ri = __shfl_sync(~0u, layer * SEQ + (wg * 2 + ((g >> 1) & 1)) * 512 + (mb * 16 + 4 * (warp & 3) + (g >> 2)) * 2 + (g & 1), lane);
        mbar_wait(bar_wo, 0);
        if (wg) mbar_wait(bar_pv, 0);
        if (wg) asm volatile("bar.sync 2, 128;" ::: "memory"); else asm volatile("bar.sync 1, 128;" ::: "memory");
        TSTAMP2(2);
#pragma unroll
        for (int q = 0; q < 8; q++) {
            uint32_t bo = wo_off(0) >> 4;
            if (q) {
                mbar_wait(bar_f2 + 64 * wg + 8 * q, 0);
                asm volatile("ld.shared.u32 %0, [%1];" : "=r"(bo) : "r"(que + 32 * wg + 4 * q) : "memory");
                bo = __shfl_sync(~0u, bo, 0);
                TSTAMP4(q);
                if (q == 1 && (tid & 127) == 0) DBGC(29 + 8 * wg);
            }
            wgmma_fence();
#pragma unroll
            for (int j = 0; j < 5; j++) wgmma_n80(ac2, (j < 4 ? da0 : da1) + (q == 7 ? o7 : 0u) + (uint64_t)((q < 6 ? q * 640 : 0) + (j & 2) * 16 + (j & 1) * 2), (j < 4 ? db0 : db1) + bo + (uint64_t)((j & 2) * 160 + (j & 1) * 32), j || q);
            wgmma_commit();
            if (q == 0) {
                wgmma_wait<0>();
                if ((tid & 127) == 0) { mbar_arrive(bar_e2 + 16 * wg); mbar_arrive(bar_e2 + 8); }
            }
            if (q == 2 && wg) {
                wgmma_wait<1>();
                if (tid == 128) mbar_arrive(bar_e2 + 24);
            }
        }
        if ((tid & 127) == 0) DBGC(28 + wg * 8 + 7);
        TSTAMP2(3);
        wgmma_wait<0>();
        TSTAMP2(4);
        if (__any_sync(~0u, ac2[0] != ac2[0] || ac2[2] != ac2[2])) {
#pragma unroll
            for (int i = 0; i < 40; i++) ac2[i] = 0.f;
            uint32_t a[20], an[20];
            auto lda = [&](uint32_t (&r)[20], int h) {
#pragma unroll
                for (int u = 0; u < 4; u++)
                    asm volatile("ld.relaxed.gpu.global.v4.u32 {%0,%1,%2,%3}, [%4];" : "=r"(r[4 * u]), "=r"(r[4 * u + 1]), "=r"(r[4 * u + 2]), "=r"(r[4 * u + 3]) : "l"(ot + h * 20480 + o0 + u * 512) : "memory");
#pragma unroll
                for (int u = 0; u < 2; u++)
                    asm volatile("ld.relaxed.gpu.global.v2.u32 {%0,%1}, [%2];" : "=r"(r[16 + 2 * u]), "=r"(r[17 + 2 * u]) : "l"(ot + h * 20480 + o1 + u * 256) : "memory");
            };
            lda(an, 0);
#pragma unroll 5
            for (int k = lane; k < WOB / 16; k += 32)
                reinterpret_cast<uint4*>(stg + (sl - sbase))[k] = __ldcg(reinterpret_cast<const uint4*>(wo + hg * 8 * WOB) + k);
            __syncwarp();
#pragma unroll 1
            for (int h = 0; h < 8; h++) {
#pragma unroll 1
                for (int it = 0; it < SPIN_MAX; it++) {
                    uint32_t m = 0;
#pragma unroll
                    for (int k = 0; k < 20; k += 2) m = __vimax3_u32(m, an[k], an[k + 1]);
                    if (!__any_sync(~0u, m == ~0u)) break;
                    lda(an, h);
                }
#pragma unroll
                for (int k = 0; k < 20; k++) a[k] = an[k];
                lda(an, min(h + 1, 7));
                const uint32_t bp = h == hg ? sl : sbase + wo_off(h + (h < hg));
                const int r0 = 8 * ((lane & 7) >> 1) + 2 * (lane >> 3) + (lane & 1), r2 = 4 * ((lane & 7) >> 1) + 2 * ((lane >> 3) & 1) + (lane & 1);
#pragma unroll
                for (int n = 0; n < 10; n++) {
                    uint32_t b[12];
                    ldsm_x4_t(b, bp + (n >> 1) * 1024 + r0 * 32 + (((n ^ (r0 >> 2)) & 1) << 4));
                    ldsm_x4_t(b + 4, bp + 5120 + (n >> 1) * 1024 + r0 * 32 + (((n ^ (r0 >> 2)) & 1) << 4));
                    ldsm_x4_t(b + 8, bp + 10240 + (n >> 1) * 512 + r2 * 32 + (((n ^ (r2 >> 2)) & 1) << 4));
                    mma_bf16(ac2 + 4 * n, a[0], a[8], a[1], a[9], b[0], b[1]); mma_bf16(ac2 + 4 * n, a[2], a[10], a[3], a[11], b[2], b[3]);
                    mma_bf16(ac2 + 4 * n, a[4], a[12], a[5], a[13], b[4], b[5]); mma_bf16(ac2 + 4 * n, a[6], a[14], a[7], a[15], b[6], b[7]);
                    mma_bf16(ac2 + 4 * n, a[16], a[18], a[17], a[19], b[8], b[9]);
                }
            }
        }
#pragma unroll
        for (int j = 0; j < 10; j++)
#pragma unroll
            for (int hh = 0; hh < 2; hh++) {
                const uint32_t a = pack2(ac2[4 * j + 2 * hh], ac2[4 * j + 2 * hh + 1]);
                const __nv_bfloat162 r = __hadd2_rn(*reinterpret_cast<const __nv_bfloat162*>(&xr[j][hh]), *reinterpret_cast<const __nv_bfloat162*>(&a));
                xr[j][hh] = *reinterpret_cast<const uint32_t*>(&r);
            }
        const uint32_t so = sl + 30720;
#pragma unroll
        for (int j = 0; j < 10; j += 2) stsm_x4_t(so + trow + 1024 * j, xr[j][0], xr[j][1], xr[j + 1][0], xr[j + 1][1]);
        fence_async_smem();
        if (wg) asm volatile("bar.sync 2, 128;" ::: "memory"); else asm volatile("bar.sync 1, 128;" ::: "memory");
        TSTAMP2(5);
        if ((tid & 127) == 0) {
            asm volatile("cp.async.bulk.tensor.2d.global.shared::cta.bulk_group [%0, {%1, %2}], [%3];" ::"l"(&tmX1), "r"(mb * 128 + 64 * wg), "r"(hg * 80), "r"(so) : "memory");
            asm volatile("cp.async.bulk.commit_group;" ::: "memory");
        }
        __syncwarp();
        const float p0 = *(volatile const float*)&rw[g].x, p1 = *(volatile const float*)&rw[g + 8].x;
        float s[3][4] = {};
        const uint32_t pp[2] = {__byte_perm(__float_as_uint(p0), 0, 0x3232), __byte_perm(__float_as_uint(p1), 0, 0x3232)};
#pragma unroll
        for (int j = 0; j < 10; j += 2) {
            const uint32_t d0 = sub2(xr[j][0], pp[0]), d1 = sub2(xr[j][1], pp[1]), d2 = sub2(xr[j + 1][0], pp[0]), d3 = sub2(xr[j + 1][1], pp[1]);
            mma_bf16(s[0], xr[j][0], xr[j][1], xr[j + 1][0], xr[j + 1][1], 0x3f803f80u, 0x3f803f80u);
            mma_bf16(s[1], d0, d1, d2, d3, d0, d2);
            mma_bf16(s[2], d0, d1, d2, d3, d1, d3);
        }
        if (t == (g >> 1)) {
            float2* rp = rsum + ri;
            asm volatile("red.relaxed.gpu.global.add.v2.f32 [%0], {%1, %2};" ::"l"(rp), "f"(fmaf(-80.f, p0, s[0][0])), "f"((g & 1) ? s[1][1] : s[1][0]) : "memory");
            asm volatile("red.relaxed.gpu.global.add.v2.f32 [%0], {%1, %2};" ::"l"(rp + 4), "f"(fmaf(-80.f, p1, s[0][2])), "f"((g & 1) ? s[2][3] : s[2][2]) : "memory");
        }
        asm volatile("cp.async.bulk.wait_group.read 0;" ::: "memory");
        TSTAMP2(6);
        if (tid == 0) DBGC(63);
        if (tid == 128) DBGC(28);
        if (tid == 0) DBGCAL(2);
        GSTAMP(g_tim1, 14);
        SPAN(1 + 4 * layer, 3);
    }
}

static int h_nsm;
static void* h_sym[11];
static TileTab h_tab;
static CUtensorMap h_tmX0, h_tmX1, h_tmR0, h_tmR1, h_tmX1st, h_tmOut, h_tmWq, h_tmWo, h_tmWt;
typedef CUresult (*PFN_encodeTiled)(CUtensorMap*, CUtensorMapDataType, cuuint32_t, void*, const cuuint64_t*, const cuuint64_t*,
                                    const cuuint32_t*, const cuuint32_t*, CUtensorMapInterleave, CUtensorMapSwizzle,
                                    CUtensorMapL2promotion, CUtensorMapFloatOOBfill);
static void make_tmap(CUtensorMap* tm, const void* ptr, uint64_t cols, uint64_t rows, uint32_t bc, uint32_t br, CUtensorMapSwizzle sw, uint64_t pitch = 0, uint64_t hi = 0, uint32_t bh = 2) {
    static PFN_encodeTiled fn = nullptr;
    if (!fn) {
        void* p = nullptr; cudaDriverEntryPointQueryResult qr;
        cudaGetDriverEntryPoint("cuTensorMapEncodeTiled", &p, cudaEnableDefault, &qr);
        fn = (PFN_encodeTiled)p;
    }
    if (br == 0) {
        cuuint64_t dims[5] = {16, 2, rows / 8, 4, cols / 16}; cuuint64_t strides[4] = {cols * 2, cols * 16, cols * 4, 32};
        cuuint32_t box[5] = {16, 2, bc, 4, 5}; cuuint32_t es[5] = {1, 1, 1, 1, 1};
        fn(tm, CU_TENSOR_MAP_DATA_TYPE_BFLOAT16, 5, const_cast<void*>(ptr), dims, strides, box, es, CU_TENSOR_MAP_INTERLEAVE_NONE, sw,
           CU_TENSOR_MAP_L2_PROMOTION_L2_128B, CU_TENSOR_MAP_FLOAT_OOB_FILL_NONE);
        return;
    }
    if (bh == 0) {
        cuuint64_t dims[5] = {64, 64, 2, 16, 10}; cuuint64_t strides[4] = {pitch * 2, hi * 2, cols * 2, rows * 2};
        cuuint32_t box[5] = {64, 64, 2, 1, 1}; cuuint32_t es[5] = {1, 1, 1, 1, 1};
        fn(tm, CU_TENSOR_MAP_DATA_TYPE_BFLOAT16, 5, const_cast<void*>(ptr), dims, strides, box, es, CU_TENSOR_MAP_INTERLEAVE_NONE, sw,
           CU_TENSOR_MAP_L2_PROMOTION_L2_128B, CU_TENSOR_MAP_FLOAT_OOB_FILL_NONE);
        return;
    }
    if (hi) {
        cuuint64_t dims[3] = {cols, rows, hi == 64 ? 32u : hi == 16 ? 120u : 2u}; cuuint64_t strides[2] = {pitch * 2, hi * 2};
        cuuint32_t box[3] = {bc, br, bh}; cuuint32_t es[3] = {1, 1, 1};
        fn(tm, CU_TENSOR_MAP_DATA_TYPE_BFLOAT16, 3, const_cast<void*>(ptr), dims, strides, box, es, CU_TENSOR_MAP_INTERLEAVE_NONE, sw,
           CU_TENSOR_MAP_L2_PROMOTION_L2_128B, CU_TENSOR_MAP_FLOAT_OOB_FILL_NONE);
        return;
    }
    cuuint64_t dims[2] = {cols, rows}; cuuint64_t strides[1] = {(pitch ? pitch : cols) * 2};
    cuuint32_t box[2] = {bc, br}; cuuint32_t es[2] = {1, 1};
    fn(tm, CU_TENSOR_MAP_DATA_TYPE_BFLOAT16, 2, const_cast<void*>(ptr), dims, strides, box, es, CU_TENSOR_MAP_INTERLEAVE_NONE, sw,
       CU_TENSOR_MAP_L2_PROMOTION_L2_128B, CU_TENSOR_MAP_FLOAT_OOB_FILL_NONE);
}
template <typename... Args>
static void launch_pdl(void (*kern)(Args...), int grid, int block, int smem, Args... args) {
    cudaLaunchConfig_t cfg = {};
    cfg.gridDim = dim3(grid); cfg.blockDim = dim3(block); cfg.dynamicSmemBytes = smem; cfg.stream = cudaStreamPerThread;
    cudaLaunchAttribute at[1];
    at[0].id = cudaLaunchAttributeProgrammaticStreamSerialization; at[0].val.programmaticStreamSerializationAllowed = 1;
    cfg.attrs = at; cfg.numAttrs = 1;
    cudaLaunchKernelEx(&cfg, kern, args...);
}
static void launch_stage(int k, void* const* d_in, void* d_out) {
    const KgIn kg = {(const bf16*)d_in[4], (const bf16*)d_in[5], (const bf16*)d_in[6], (const bf16*)d_in[7], (const bf16*)d_in[8], (const bf16*)d_in[9], (const bf16*)d_in[0], (const bf16*)d_in[1], (const bf16*)d_in[2],
                      (uint4*)h_sym[0], (uint4*)h_sym[1], (uint4*)h_sym[2], (uint4*)h_sym[3], (uint4*)h_sym[4], (float*)h_sym[5]};
    switch (k) {
        case 0: kgen_kernel<<<128, 512, KG_SMEM, cudaStreamPerThread>>>(kg, h_tmWq, h_tmWo, h_tmWt); break;
        case 1: launch_pdl(a1_kernel, h_nsm, A1_THREADS, A1_SMEM, 0, (const bf16*)d_in[0], (const unsigned char*)h_sym[1], (const unsigned char*)h_sym[2], (float2*)h_sym[4], (uint4*)h_sym[6], h_tmX0, h_tmR0, h_tmX1st, h_tab); break;
        case 3: launch_pdl(conv_kernel, DM / CV_CPB, CV_THREADS, CV_SMEM, 0, (const uint4*)h_sym[7], (const float4*)h_sym[4], (const bf16*)h_sym[8], (bf16*)h_sym[9], (const uint4*)h_sym[0], h_tmOut); break;
        case 5: launch_pdl(a1_kernel, h_nsm, A1_THREADS, A1_SMEM, 1, (const bf16*)d_in[0], (const unsigned char*)h_sym[1], (const unsigned char*)h_sym[2], (float2*)h_sym[4], (uint4*)h_sym[6], h_tmX1, h_tmR1, h_tmX1st, h_tab); break;
        case 7: launch_pdl(conv_kernel, DM / CV_CPB, CV_THREADS, CV_SMEM, 1, (const uint4*)h_sym[7] + SEQ / 8, (const float4*)h_sym[4] + SEQ / 2, (const bf16*)h_sym[8], (bf16*)h_sym[10], (const uint4*)h_sym[0], h_tmOut); break;
        default: break;
    }
}
static int n_stage_kernels() { return 9; }
static const char* stage_name(int k) { const char* n[] = {"kgen", "a1", "a2", "conv", "tr", "a1", "a2", "conv", "tr"}; return n[k]; }

extern "C" void kernel_launch(void* const* d_in, const int* in_sizes, int n_in, void* d_out, int out_size) {
    (void)in_sizes; (void)n_in; (void)out_size;
    static const void *p_in = nullptr, *p_w1 = nullptr, *p_w2 = nullptr, *p_out = nullptr;
    if (p_in != d_in[0] || p_w1 != d_in[1] || p_w2 != d_in[2] || p_out != d_out) {
        cudaFuncSetAttribute(conv_kernel, cudaFuncAttributeMaxDynamicSharedMemorySize, CV_SMEM);
        cudaFuncSetAttribute(kgen_kernel, cudaFuncAttributeMaxDynamicSharedMemorySize, KG_SMEM);
        cudaFuncSetAttribute(a1_kernel, cudaFuncAttributeMaxDynamicSharedMemorySize, A1_SMEM);
        int dev; cudaGetDevice(&dev); cudaDeviceGetAttribute(&h_nsm, cudaDevAttrMultiProcessorCount, dev);
        if (h_nsm != 132) h_nsm = 128;
        h_tab.ns = h_nsm == 132 ? 132 : ~0u;
        for (int i = 0; i < 264; i++) {
            const int h = (i - 64) >> 1;
            const int t = i >= 132 ? i - 132 : i < 64 ? ((i >> 1) & 7) * 16 + (i >> 4) * 2 + (i & 1) : i < 120 ? (1 + h % 7) * 16 + 8 + (h / 7) * 2 + (i & 1) : i < 124 ? 128 : i - 116;
            const int hg = (4 * (t >> 6) + (t & 3)) & 7;
            h_tab.e[i] = {(unsigned char)((t >> 2) & 15), (unsigned char)hg, (unsigned char)(5 * (hg >> 2)), (unsigned char)t, (uint32_t)(hg * 10 * WQ_STAGE)};
        }
        cudaGetSymbolAddress(&h_sym[0], g_tap); cudaGetSymbolAddress(&h_sym[1], g_wq); cudaGetSymbolAddress(&h_sym[2], g_wo);
        cudaGetSymbolAddress(&h_sym[3], g_halo); cudaGetSymbolAddress(&h_sym[4], g_sum); cudaGetSymbolAddress(&h_sym[5], g_csp); cudaGetSymbolAddress(&h_sym[6], g_of);
        cudaGetSymbolAddress(&h_sym[7], g_piv); cudaGetSymbolAddress(&h_sym[8], g_x1T); cudaGetSymbolAddress(&h_sym[9], g_xcT); cudaGetSymbolAddress(&h_sym[10], g_yT);
        void *px1, *px2;
        cudaGetSymbolAddress(&px1, g_x1T); cudaGetSymbolAddress(&px2, g_xcT);
        make_tmap(&h_tmX0, d_in[0], 128 * 640, 64, 64, 64, CU_TENSOR_MAP_SWIZZLE_128B, 1280, 640, 0);
        make_tmap(&h_tmX1, px2, 128, 64 * XCP, 64, 64, CU_TENSOR_MAP_SWIZZLE_128B, XCP, 64, 0);
        make_tmap(&h_tmR0, d_in[0], 640, 1024, 80, 64, CU_TENSOR_MAP_SWIZZLE_NONE, 1280, 640, 1);
        make_tmap(&h_tmR1, px2, 64, 640, 64, 80, CU_TENSOR_MAP_SWIZZLE_128B, XCP, 64, 1);
        make_tmap(&h_tmX1st, px1, 2048, 640, 64, 80, CU_TENSOR_MAP_SWIZZLE_128B, XCP);
        make_tmap(&h_tmWq, d_in[1], 16, 640, 16, 32, CU_TENSOR_MAP_SWIZZLE_32B, 1920, 16, 5);
        make_tmap(&h_tmWo, d_in[2], 640, 640, 4, 0, CU_TENSOR_MAP_SWIZZLE_32B);
        make_tmap(&h_tmWt, d_in[2], 640, 640, 2, 0, CU_TENSOR_MAP_SWIZZLE_32B);
        make_tmap(&h_tmOut, d_out, 640, 1024, 80, 8, CU_TENSOR_MAP_SWIZZLE_NONE, 1280, 640, 1);
        p_in = d_in[0]; p_w1 = d_in[1]; p_w2 = d_in[2]; p_out = d_out;
    }
    for (int k = 0; k < n_stage_kernels(); k++) launch_stage(k, d_in, d_out);
}
```

```cpp
#include <cuda_runtime.h>
#include <cuda_bf16.h>
#include <stdint.h>
#include <cuda.h>

typedef __nv_bfloat16 bf16;

constexpr int SEQ = 2048;
constexpr int DM = 640;
constexpr int NMODE = 192;

__device__ __forceinline__ float bf2f(bf16 v) { return __bfloat162float(v); }
__device__ __forceinline__ float rbf(float v) {
    uint32_t r;
    asm("cvt.rn.bf16x2.f32 %0, %1, %2;" : "=r"(r) : "f"(v), "f"(0.f));
    return __uint_as_float(r);
}
__device__ __forceinline__ uint32_t pack2(float lo, float hi) {
    __nv_bfloat162 t = __floats2bfloat162_rn(lo, hi);
    return *reinterpret_cast<uint32_t*>(&t);
}
__device__ __forceinline__ void pdl_sync() {
    asm volatile("griddepcontrol.wait;" ::: "memory");
    asm volatile("griddepcontrol.launch_dependents;" ::: "memory");
}
__device__ __forceinline__ float sqrt_apx(float v) { float r; asm("sqrt.approx.ftz.f32 %0, %1;" : "=f"(r) : "f"(v)); return r; }
__device__ __forceinline__ float rcp_apx(float v) { float r; asm("rcp.approx.ftz.f32 %0, %1;" : "=f"(r) : "f"(v)); return r; }
__device__ __forceinline__ uint32_t smem_u32(const void* p) { return (uint32_t)__cvta_generic_to_shared(p); }

constexpr int TAPB = 2 * 152 * 8;
__device__ __align__(128) uint4 g_tap[DM * 128];
#define XPAD 64
constexpr int XCP = SEQ + XPAD;
__device__ __align__(128) bf16 g_x1T[DM * XCP];
__device__ __align__(128) bf16 g_xcT[DM * XCP];
__device__ __align__(128) uint4 g_of[128 * 1280];
constexpr int WQ_STAGE = 240 * 128, WOB = 80 * 160;
__device__ __align__(128) uint4 g_wq[8 * 10 * WQ_STAGE / 16];
__device__ __align__(128) uint4 g_wo[64 * WOB / 16];
__device__ __align__(16) float g_csp[10 * 1920];
#define FSTR 32
__device__ __align__(128) float2 g_sum[2 * SEQ + 256 * FSTR];
__device__ __align__(16) bf16 g_piv[2 * SEQ];
__device__ __align__(128) bf16 g_yT[DM * XCP];
__device__ uint32_t g_epoch;
__device__ __align__(16) unsigned long long g_rstat[SEQ];
__device__ __align__(128) uint4 g_halo[640 * 148];
__device__ __forceinline__ unsigned long long tagw(uint32_t payload, uint32_t tag) { return ((unsigned long long)tag << 32) | payload; }
__device__ __forceinline__ ulonglong2 ld_tag2(const ulonglong2* p) {
    ulonglong2 v;
    asm volatile("ld.relaxed.gpu.global.v2.u64 {%0, %1}, [%2];" : "=l"(v.x), "=l"(v.y) : "l"(p) : "memory");
    return v;
}
__device__ __forceinline__ bool tag_ok(ulonglong2 v, uint32_t tag) { return (uint32_t)(v.x >> 32) == tag && (uint32_t)(v.y >> 32) == tag; }
__device__ __forceinline__ uint32_t ld_epoch() { uint32_t v; asm volatile("ld.relaxed.gpu.global.u32 %0, [%1];" : "=r"(v) : "l"(&g_epoch) : "memory"); return v + 1; }
constexpr int SPIN_MAX = 1 << 20;
__device__ uint32_t g_started[4];
__device__ __forceinline__ void sm_started(int slot) { asm volatile("red.relaxed.gpu.global.add.u32 [%0], 1;" ::"l"(g_started + slot) : "memory"); }
__device__ __noinline__ void sm_idle(int slot) {
    if (threadIdx.x) return;
    sm_started(slot);
    const uint32_t want = ld_epoch() * gridDim.x;
    pdl_sync();
#pragma unroll 1
    for (int it = 0; it < SPIN_MAX; it++) {
        uint32_t v;
        asm volatile("ld.relaxed.gpu.global.u32 %0, [%1];" : "=r"(v) : "l"(g_started + slot) : "memory");
        if ((int)(v - want) >= 0) break;
        __nanosleep(100);
    }
}
struct TileTab { uint32_t ns, pad; struct { unsigned char mb, hg, kb0, tile; uint32_t woff; } __align__(8) e[264]; };
__device__ __forceinline__ bool elect() {
    uint32_t p;
    asm volatile("{\n.reg .pred p;\nelect.sync _|p, 0xffffffff;\nselp.b32 %0, 1, 0, p;\n}" : "=r"(p));
    return p;
}
#define DBG_SYMS
#define TSTAMP(i)
#define TSTAMP1(i)
#define TSTAMP1T(i, t)
#define TSTAMP1X(i, t)
#define SPAN(k, i)
#define GSTAMP(arr, i)
#define TSTAMP2(i)
#define TSTAMP3(i)
#define TSTAMP4(i)
#define TSTAMPK(i, t)
#define TSTAMPC(i)
#define DBGC(i)
#define DBGV(i, v)
#define DBGCAL(i)

#define CST(i)
#define CST_END
#define CST_EXTRA 0
__device__ __forceinline__ void mma_bf16(float* d, uint32_t a0, uint32_t a1, uint32_t a2, uint32_t a3, uint32_t b0, uint32_t b1) {
    asm volatile("mma.sync.aligned.m16n8k16.row.col.f32.bf16.bf16.f32 {%0,%1,%2,%3}, {%4,%5,%6,%7}, {%8,%9}, {%0,%1,%2,%3};"
                 : "+f"(d[0]), "+f"(d[1]), "+f"(d[2]), "+f"(d[3]) : "r"(a0), "r"(a1), "r"(a2), "r"(a3), "r"(b0), "r"(b1));
}
__device__ __forceinline__ void mma_bf16_k8(float* d, uint32_t a0, uint32_t a1, uint32_t b0) {
    asm volatile("mma.sync.aligned.m16n8k8.row.col.f32.bf16.bf16.f32 {%0,%1,%2,%3}, {%4,%5}, {%6}, {%0,%1,%2,%3};"
                 : "+f"(d[0]), "+f"(d[1]), "+f"(d[2]), "+f"(d[3]) : "r"(a0), "r"(a1), "r"(b0));
}
__device__ __forceinline__ void ldsm_x4(uint32_t* r, uint32_t addr) {
    asm volatile("ldmatrix.sync.aligned.m8n8.x4.shared.b16 {%0,%1,%2,%3}, [%4];"
                 : "=r"(r[0]), "=r"(r[1]), "=r"(r[2]), "=r"(r[3]) : "r"(addr));
}

__device__ __forceinline__ void ldsm_x4_t(uint32_t* r, uint32_t addr) {
    asm volatile("ldmatrix.sync.aligned.m8n8.x4.trans.shared.b16 {%0,%1,%2,%3}, [%4];"
                 : "=r"(r[0]), "=r"(r[1]), "=r"(r[2]), "=r"(r[3]) : "r"(addr));
}
__device__ __forceinline__ void mbar_init(uint32_t bar, int count) { asm volatile("mbarrier.init.shared::cta.b64 [%0], %1;" ::"r"(bar), "r"(count)); }
__device__ __forceinline__ void mbar_arrive(uint32_t bar) { asm volatile("mbarrier.arrive.shared::cta.b64 _, [%0];" ::"r"(bar) : "memory"); }
__device__ __forceinline__ void mbar_wait(uint32_t bar, uint32_t parity) {
    asm volatile("{\n.reg .pred p;\nWAIT_LOOP:\n"
                 "mbarrier.try_wait.parity.shared::cta.b64 p, [%0], %1;\n"
                 "@p bra.uni WAIT_DONE;\nbra.uni WAIT_LOOP;\nWAIT_DONE:\n}" ::"r"(bar), "r"(parity) : "memory");
}

__device__ __forceinline__ void mbar_expect_tx(uint32_t bar, uint32_t bytes) {
    asm volatile("mbarrier.arrive.expect_tx.shared::cta.b64 _, [%0], %1;" ::"r"(bar), "r"(bytes) : "memory");
}
__device__ __forceinline__ void tma_load_2d(uint32_t dst, const void* tmap, int c0, int c1, uint32_t bar) {
    asm volatile("cp.async.bulk.tensor.2d.shared::cluster.global.mbarrier::complete_tx::bytes [%0], [%1, {%3, %4}], [%2];"
                 ::"r"(dst), "l"(tmap), "r"(bar), "r"(c0), "r"(c1) : "memory");
}
__device__ __forceinline__ void tma_load_3d(uint32_t dst, const void* tmap, int c0, int c1, int c2, uint32_t bar) {
    asm volatile("cp.async.bulk.tensor.3d.shared::cluster.global.mbarrier::complete_tx::bytes [%0], [%1, {%3, %4, %5}], [%2];"
                 ::"r"(dst), "l"(tmap), "r"(bar), "r"(c0), "r"(c1), "r"(c2) : "memory");
}
__device__ __forceinline__ void fence_async_smem() { asm volatile("fence.proxy.async.shared::cta;" ::: "memory"); }
__device__ __forceinline__ void bulk_load(uint32_t dst, const void* src, uint32_t bytes, uint32_t bar) {
    asm volatile("cp.async.bulk.shared::cluster.global.mbarrier::complete_tx::bytes [%0], [%1], %2, [%3];"
                 ::"r"(dst), "l"(src), "r"(bytes), "r"(bar) : "memory");
}
__device__ __forceinline__ void stsm_x4(uint32_t addr, uint32_t r0, uint32_t r1, uint32_t r2, uint32_t r3) {
    asm volatile("stmatrix.sync.aligned.m8n8.x4.shared.b16 [%0], {%1,%2,%3,%4};" ::"r"(addr), "r"(r0), "r"(r1), "r"(r2), "r"(r3) : "memory");
}
__device__ __forceinline__ void stsm_x4_t(uint32_t addr, uint32_t r0, uint32_t r1, uint32_t r2, uint32_t r3) {
    asm volatile("stmatrix.sync.aligned.m8n8.x4.trans.shared.b16 [%0], {%1,%2,%3,%4};" ::"r"(addr), "r"(r0), "r"(r1), "r"(r2), "r"(r3) : "memory");
}
__device__ __forceinline__ void prefetch_tmap(const void* tmap) { asm volatile("prefetch.tensormap [%0];" ::"l"(tmap) : "memory"); }

__device__ __forceinline__ float2 cexp_at(float wr2, float wi, float p) {
    float er;
    asm("ex2.approx.ftz.f32 %0, %1;" : "=f"(er) : "f"(wr2 * p));
    float th = wi * p;
    const float k = rintf(th * 0.15915494309189535f);
    th = fmaf(k, -6.2831854820251465f, th);
    th = fmaf(k, 1.7484555314695172e-7f, th);
    return make_float2(er * __cosf(th), er * __sinf(th));
}
__device__ __forceinline__ float2 cmul(float2 a, float2 b) {
    return make_float2(fmaf(a.x, b.x, -a.y * b.y), fmaf(a.x, b.y, a.y * b.x));
}
__device__ __forceinline__ float2 csqr(float2 a) { return make_float2(fmaf(a.x, a.x, -a.y * a.y), (a.x + a.x) * a.y); }
__device__ __forceinline__ uint32_t packh(float2 v) {
    uint32_t r;
    asm("cvt.rn.f16x2.f32 %0, %1, %2;" : "=r"(r) : "f"(v.y), "f"(v.x));
    return r;
}
__device__ __forceinline__ void mma_f16(float* d, uint32_t a0, uint32_t a1, uint32_t a2, uint32_t a3, uint32_t b0, uint32_t b1) {
    asm volatile("mma.sync.aligned.m16n8k16.row.col.f32.f16.f16.f32 {%0,%1,%2,%3}, {%4,%5,%6,%7}, {%8,%9}, {%0,%1,%2,%3};"
                 : "+f"(d[0]), "+f"(d[1]), "+f"(d[2]), "+f"(d[3]) : "r"(a0), "r"(a1), "r"(a2), "r"(a3), "r"(b0), "r"(b1));
}

struct KgIn { const bf16 *logA, *Aim, *Cre, *Cim, *logdt, *dsk, *x, *wqkv, *wo; uint4 *tap, *wq, *wop, *halo, *sum; float* csp; };
constexpr int KG_THREADS = NMODE / 2;

constexpr int KG_BUF = 15 * 12288, KG_BAR = KG_BUF + 6 * 5120, KG_SMEM = KG_BAR + 64;
__global__ void __launch_bounds__(512, 1) kgen_kernel(const KgIn in, const __grid_constant__ CUtensorMap tmWq, const __grid_constant__ CUtensorMap tmWo,
                                                        const __grid_constant__ CUtensorMap tmWt) {
    extern __shared__ __align__(1024) uint4 tabs[];
#define KG_ROT 0
    const int lane = threadIdx.x & 31, w16 = (__shfl_sync(~0u, threadIdx.x >> 5, 0) + KG_ROT) & 15, grp = w16 / 3, warp = w16 - 3 * grp;
    const int d = blockIdx.x * 5 + grp, tid = warp * 32 + lane;
    uint4* tab = tabs + grp * (3 * 768);
    SPAN(0, 0); SPAN(0, 1);
    TSTAMPK(0, 0);
    asm volatile("griddepcontrol.launch_dependents;" ::: "memory");
    if (w16 == 15) {
        const uint32_t b0 = smem_u32(tab), wbar = b0 + 6 * 5120;
        const int blk = blockIdx.x, nq = blk < 112 ? 4 : 2, nj = nq + (blk < 64 ? 1 : 2);
        auto fetch = [&](int i) {
            const uint32_t dst = b0 + i * 5120, bar = wbar + 8 * i;
            if (i < nq) {
                const int p = blk + 64 * (i & 2), kb = p / 24;
                mbar_expect_tx(bar, 5120);
                tma_load_3d(dst, &tmWq, 0, kb * 64 + (i & 1) * 32, (p - 24 * kb) * 5, bar);
            } else if (i < nj) {
                const int o = i == nq ? blk : 255 - blk;
                mbar_expect_tx(bar, o < 128 ? 5120 : 2560);
                asm volatile("cp.async.bulk.tensor.5d.shared::cluster.global.mbarrier::complete_tx::bytes [%0], [%1, {%3, %3, %4, %3, %5}], [%2];"
                             ::"r"(dst), "l"(o < 128 ? &tmWo : &tmWt), "r"(bar), "r"(0), "r"((o & 7) * 10 + (o >> 6) * 4), "r"(((o >> 3) & 7) * 5) : "memory");
            }
        };
        const bool one = elect();
        if (one) {
#pragma unroll
            for (int i = 0; i < 6; i++) mbar_init(wbar + 8 * i, 1);
            asm volatile("fence.mbarrier_init.release.cluster;" ::: "memory");
#pragma unroll
            for (int i = 0; i < 6; i++) fetch(i);
        }
        __syncwarp();
#pragma unroll
        for (int i = 1; i <= 5; i++) asm volatile("bar.arrive %0, 128;" ::"r"(i) : "memory");
        if (one) {
#pragma unroll 1
            for (int i = 0; i < nj; i++) {
                const int p = blk + 64 * (i & 2), kb = p / 24, hg = p & 7, sec = (p - 24 * kb) >> 3, o = i == nq ? blk : 255 - blk, cg = (o >> 3) & 7, hb = o & 7;
                const unsigned char* dst = i < nq ? reinterpret_cast<unsigned char*>(in.wq) + (hg * 10 + (hg < 4 ? kb : kb < 5 ? kb + 5 : kb - 5)) * WQ_STAGE + ((i & 1) * 3 + sec) * 5120
                                                  : reinterpret_cast<unsigned char*>(in.wop) + (cg * 8 + (hb == cg ? 0 : hb + (hb < cg))) * WOB + (o >> 6) * 5120;
                mbar_wait(wbar + 8 * i, 0);
                if (i == 0) TSTAMPK(2, (15 - KG_ROT) * 32);
                if (i == 3) TSTAMPK(5, (15 - KG_ROT) * 32);
                asm volatile("cp.async.bulk.global.shared::cta.bulk_group [%0], [%1], %2;" ::"l"(dst), "r"(b0 + i * 5120), "r"(i < nq || o < 128 ? 5120 : 2560) : "memory");
            }
            asm volatile("cp.async.bulk.commit_group;" ::: "memory");
            asm volatile("cp.async.bulk.wait_group.read 0;" ::: "memory");
        }
        TSTAMPK(11, (15 - KG_ROT) * 32);
        return;
    }
    const bf16 pdt = in.logdt[d], pdsk = in.dsk[d];
    const uint32_t pla = reinterpret_cast<const uint32_t*>(in.logA)[d * KG_THREADS + tid], pai = reinterpret_cast<const uint32_t*>(in.Aim)[d * KG_THREADS + tid];
    const uint32_t pcr = reinterpret_cast<const uint32_t*>(in.Cre)[d * KG_THREADS + tid], pci = reinterpret_cast<const uint32_t*>(in.Cim)[d * KG_THREADS + tid];
    const bf16* pfq = tid < 30 ? in.wqkv + (size_t)(d * 30 + tid) * 64 : tid < 40 ? in.wo + (size_t)(d * 10 + tid - 30) * 64 : in.x + (size_t)(d * 32 + tid - 40) * 64;
#define KG_PF 0
    if (tid < (KG_PF == 3 ? 0 : KG_PF ? 40 : 72)) asm volatile("prefetch.global.L2 [%0];" ::"l"(pfq));
    asm volatile("st.global.v4.u32 [%0], {%1,%1,%1,%1};" ::"l"(in.halo + d * 148 + tid), "r"(~0u));
    if (tid < 52) asm volatile("st.global.v4.u32 [%0], {%1,%1,%1,%1};" ::"l"(in.halo + d * 148 + 96 + tid), "r"(~0u));
    else if (w16 == 2) {
        if (lane < 16) in.sum[blockIdx.x * 16 + lane] = make_uint4(0, 0, 0, 0);
        else if (lane < 20) reinterpret_cast<uint32_t*>(in.sum + 2048)[(blockIdx.x * 4 + lane - 16) * FSTR] = 0;
    }
    const uint32_t tw = smem_u32(tab) + warp * 12288;
    const int g = lane >> 2, t = lane & 3;
    const uint32_t sta = tw + lane * 128 + ((2 * (lane & 3) + ((lane >> 2) & 1)) << 4);
    const uint32_t lda = tw + t * 128 + ((g ^ (2 * t)) << 4);
    const uint32_t stb = tw + lane * 8, ldb = tw + g * 512 + (g & 3) * 32 + t * 8;
    auto sts4 = [&](int e, int off, uint32_t a, uint32_t b, uint32_t c, uint32_t dd) {
        asm volatile("st.shared.v4.u32 [%0], {%1,%2,%3,%4};" ::"r"((sta ^ (e << 4)) + off), "r"(a), "r"(b), "r"(c), "r"(dd) : "memory");
    };
    auto lds4 = [&](int sp, int off, uint32_t* r) {
        asm volatile("ld.shared.v4.u32 {%0,%1,%2,%3}, [%4];" : "=r"(r[0]), "=r"(r[1]), "=r"(r[2]), "=r"(r[3]) : "r"((lda ^ ((sp & 1) << 4)) + sp * 512 + off) : "memory");
    };
    const float dt = rbf(expf(bf2f(pdt)));
    float2 C[2], y1[2], z8[2], y128[2];
    float cmax = 0.f;
#pragma unroll
    for (int m = 0; m < 2; m++) {
        const float wr2 = -rbf(expf(__uint_as_float(m ? pla & 0xffff0000u : pla << 16))) * dt * 1.4426950408889634f;
        const float wi = __uint_as_float(m ? pai & 0xffff0000u : pai << 16) * dt;
        C[m] = make_float2(__uint_as_float(m ? pcr & 0xffff0000u : pcr << 16) * dt, -__uint_as_float(m ? pci & 0xffff0000u : pci << 16) * dt);
        cmax = fmaxf(cmax, fmaxf(fabsf(C[m].x), fabsf(C[m].y)));
        y1[m] = cexp_at(wr2, -wi, 1.f); z8[m] = cexp_at(wr2, wi, 8.f); y128[m] = cexp_at(wr2, -wi, 128.f);
    }
    const int ex = min(max((int)(__reduce_max_sync(~0u, __float_as_uint(cmax)) >> 23), 20), 240);
    const float scale = __uint_as_float((uint32_t)(127 + 10 + 127 - ex) << 23), unscale = 2.0f * __uint_as_float((uint32_t)(ex - 10) << 23);
    TSTAMPK(4, 64);
    if (KG_PF >= 2 && tid >= 40 && tid < 72) asm volatile("prefetch.global.L2 [%0];" ::"l"(pfq));
    float k2048 = 0.f;
    float acc[5][4];
#pragma unroll
    for (int j = 0; j < 5; j++)
#pragma unroll
        for (int k = 0; k < 4; k++) acc[j][k] = 0.f;
    uint32_t af[8][4];
    {
        float2 h0[2], h1[2], g0[2], g1[2], g2[2], g2b[2], g3[2], g4[2], y2[2], y4[2];
#pragma unroll
        for (int m = 0; m < 2; m++) {
            h0[m] = make_float2(1.f, 0.f); h1[m] = csqr(csqr(csqr(z8[m])));
            g0[m] = make_float2(C[m].x * scale, C[m].y * scale);
            g1[m] = cmul(g0[m], y128[m]);
            const float2 y256 = csqr(y128[m]), y512 = csqr(y256);
            g2b[m] = g2[m] = cmul(g0[m], y256); g3[m] = cmul(g0[m], y512); g4[m] = cmul(g3[m], y512);
            y2[m] = csqr(y1[m]); y4[m] = csqr(y2[m]);
            const float2 y1024 = csqr(y512);
            k2048 += fmaf(g4[m].x, y1024.x, -g4[m].y * y1024.y);
        }
#pragma unroll
        for (int e = 0; e < 8; e++) {
            sts4(e, 0, packh(h0[0]), packh(h1[0]), packh(h0[1]), packh(h1[1]));
            sts4(e, 4096, packh(g0[0]), packh(g0[1]), packh(g1[0]), packh(g1[1]));
#pragma unroll
            for (int m = 0; m < 2; m++)
                if (e < 7) { h0[m] = e ? cmul(h0[m], z8[m]) : z8[m]; h1[m] = cmul(h1[m], z8[m]); g0[m] = cmul(g0[m], y1[m]); g1[m] = cmul(g1[m], y1[m]); }
            if (e < 5) k2048 += __shfl_xor_sync(~0u, k2048, 1 << e);
        }
        if (KG_PF == 1 && tid >= 40 && tid < 72) asm volatile("prefetch.global.L2 [%0];" ::"l"(pfq));
        __syncwarp();
#pragma unroll
        for (int e = 0; e < 8; e++) {
            uint32_t b[4];
            lds4(e, 0, af[e]); lds4(e, 4096, b);
            sts4(e, 8192, packh(g2[0]), packh(g2[1]), packh((e & 1) ? cmul(g3[0], y4[0]) : g3[0]), packh((e & 1) ? cmul(g3[1], y4[1]) : g3[1]));
            asm volatile("st.shared.v2.u32 [%0], {%1,%2};" ::"r"((stb ^ ((e & 3) << 5)) + e * 512), "r"(packh(g4[0])), "r"(packh(g4[1])) : "memory");
#pragma unroll
            for (int m = 0; m < 2; m++)
                if (e < 7) {
                    g2[m] = e == 3 ? cmul(g2b[m], y128[m]) : cmul(g2[m], y2[m]);
                    if (e & 1) g3[m] = cmul(g3[m], y128[m]);
                    g4[m] = cmul(g4[m], y128[m]);
                }
            mma_f16(acc[0], af[e][0], af[e][1], af[e][2], af[e][3], b[0], b[1]);
            mma_f16(acc[1], af[e][0], af[e][1], af[e][2], af[e][3], b[2], b[3]);
        }
    }
    TSTAMPK(6, 64);
    __syncwarp();
#pragma unroll
    for (int sp = 0; sp < 8; sp++) {
        uint32_t c[4], e0, e1;
        lds4(sp, 8192, c);
        asm volatile("ld.shared.v2.u32 {%0,%1}, [%2];" : "=r"(e0), "=r"(e1) : "r"(ldb ^ (sp << 5)) : "memory");
        mma_f16(acc[2], af[sp][0], af[sp][1], af[sp][2], af[sp][3], c[0], c[1]);
        mma_f16(acc[3], af[sp][0], af[sp][1], af[sp][2], af[sp][3], c[2], c[3]);
        mma_f16(acc[4], af[sp][0], af[sp][1], af[sp][2], af[sp][3], e0, e1);
    }
    {
        float* Pp = reinterpret_cast<float*>(tab + warp * 768);
        auto sw = [](int i) { return i ^ ((i >> 2) & 24); };
#pragma unroll
        for (int h = 0; h < 2; h++) {
            const int b = g + 8 * h;
            *reinterpret_cast<float2*>(Pp + sw(8 * b + 2 * t)) = make_float2(acc[0][2 * h] * unscale, acc[0][2 * h + 1] * unscale);
            *reinterpret_cast<float2*>(Pp + 128 + sw(8 * b + 2 * t)) = make_float2(acc[1][2 * h] * unscale, acc[1][2 * h + 1] * unscale);
            *reinterpret_cast<float2*>(Pp + 256 + sw(4 * b + 2 * (t & 1) + 64 * (t >> 1))) = make_float2(acc[2][2 * h] * unscale, acc[2][2 * h + 1] * unscale);
            *reinterpret_cast<float2*>(Pp + 384 + sw(2 * b + 32 * t)) = make_float2(acc[3][2 * h] * unscale, acc[3][2 * h + 1] * unscale);
            Pp[512 + sw(b + 32 * t)] = acc[4][2 * h] * unscale;
            Pp[512 + sw(b + 32 * t + 16)] = acc[4][2 * h + 1] * unscale;
        }
        if (lane == 0) Pp[640] = k2048 * unscale;
    }
    TSTAMPK(7, 64);
    asm volatile("bar.sync %0, 128;" ::"r"(grp + 1) : "memory");
    TSTAMPK(9, 64);
    const float* Kp = reinterpret_cast<const float*>(tab);
    auto ksum = [&](int i) -> float { return (Kp[i] + Kp[3072 + i]) + Kp[6144 + i]; };
    auto ksum4 = [&](int q) -> float4 {
        q ^= (q >> 2) & 6;
        const float4 a = reinterpret_cast<const float4*>(Kp)[q], b = reinterpret_cast<const float4*>(Kp)[768 + q], c = reinterpret_cast<const float4*>(Kp)[1536 + q];
        return make_float4((a.x + b.x) + c.x, (a.y + b.y) + c.y, (a.z + b.z) + c.z, (a.w + b.w) + c.w);
    };
    {
        uint2* E4 = reinterpret_cast<uint2*>(in.tap + d * 128);
        float4 v = ksum4(tid), u = ksum4(96 + min(tid, 64));
        const float cor = rbf(ksum(tid == 95 ? 384 : 512));
        if (tid == 0) v.x += bf2f(pdsk);
        if (tid == 95) v.w -= cor;
        if (tid == 31) u.w -= cor;
        const uint32_t lo = pack2(v.x, v.y), hi = pack2(v.z, v.w);
        if (tid < 64) {
            E4[6 + tid] = make_uint2(lo, hi);
            E4[(tid < 32 ? 159 : 209 - 32) + tid] = make_uint2(pack2(u.x, u.y), pack2(u.z, u.w));
        } else {
            const uint32_t nx = __shfl_down_sync(~0u, lo, 1);
            in.tap[d * 128 + 35 + tid - 64] = make_uint4(__byte_perm(lo, 0, 0x1010), __byte_perm(lo, hi, 0x5432), __byte_perm(hi, 0, 0x1010), __byte_perm(hi, tid == 95 ? 0u : nx, 0x5432));
            if (tid == 64) E4[241] = make_uint2(pack2(u.x, 0.f), 0u);
        }
    }
    TSTAMPK(10, 64);
    if (warp < (blockIdx.x < 112 ? 2 : 1)) {
        const uint32_t sb = smem_u32(tabs);
        mbar_wait(sb + KG_BAR + 16 * warp, 0); mbar_wait(sb + KG_BAR + 16 * warp + 8, 0);
        uint32_t w[4][4];
        float cs[4] = {0.f, 0.f, 0.f, 0.f};
#pragma unroll
        for (int a = 0; a < 4; a++)
            ldsm_x4_t(w[a], sb + KG_BUF + warp * 10240 + grp * 1024 + ((lane >> 4) * 8 + (lane & 7)) * 32 + ((((lane >> 3) ^ (lane >> 2)) & 1) << 4) + (a >> 1) * 5120 + (a & 1) * 512);
#pragma unroll
        for (int a = 0; a < 4; a++) mma_bf16(cs, w[a][0], w[a][1], w[a][2], w[a][3], 0x3f803f80u, 0x3f803f80u);
        if (t < 2) in.csp[(blockIdx.x + 128 * warp) * 80 + grp * 16 + g + 8 * t] = t ? cs[2] : cs[0];
    }
    SPAN(0, 3);
}

#define CV_SLEEP 100
#define CV_D2 3
#define CV_PDH 12
#define CV_PDF 4
#define CV_HAND 7
constexpr int CV_CPB = 5;
constexpr int CV_THREADS = 512;
constexpr int UPADF = 128;
constexpr int ULEN = UPADF + SEQ;
constexpr int XLEN = SEQ + 16;
constexpr int BX_5 = 0, BX_3 = 3264, BX_9 = 6528, BX_7 = 8960, BX_LEN = 11392;
constexpr int CV_SM_U = 0;
constexpr int CV_SM_T = CV_CPB * ULEN * 2;
constexpr int CV_SM_B = CV_SM_T + CV_CPB * TAPB;
constexpr int CV_SM_X = CV_SM_B + CV_CPB * BX_LEN;
constexpr int CV_SM_Y = (CV_SM_X + CV_CPB * XLEN * 2 + 127) & ~127;
constexpr int CV_SM_CNT = CV_SM_Y + CV_CPB * 8192;
constexpr int CV_SM_O = CV_SM_CNT + 128;
constexpr int CV_SMEM = CV_SM_O + 20480 + CST_EXTRA;
static_assert(ULEN % 128 == 0 && CV_SM_B % 128 == 0 && CV_SM_CNT % 128 == 0, "layout");

__device__ __forceinline__ uint32_t sub2(uint32_t x, uint32_t m) {
    const __nv_bfloat162 d = __hsub2(*reinterpret_cast<const __nv_bfloat162*>(&x), *reinterpret_cast<const __nv_bfloat162*>(&m));
    return *reinterpret_cast<const uint32_t*>(&d);
}
__device__ __forceinline__ uint32_t add2(uint32_t x, uint32_t y) {
    const __nv_bfloat162 d = __hadd2_rn(*reinterpret_cast<const __nv_bfloat162*>(&x), *reinterpret_cast<const __nv_bfloat162*>(&y));
    return *reinterpret_cast<const uint32_t*>(&d);
}
__device__ __forceinline__ void wgmma_fence() { asm volatile("wgmma.fence.sync.aligned;" ::: "memory"); }
__device__ __forceinline__ void wgmma_commit() { asm volatile("wgmma.commit_group.sync.aligned;" ::: "memory"); }
template <int N> __device__ __forceinline__ void wgmma_wait() { asm volatile("wgmma.wait_group.sync.aligned %0;" ::"n"(N) : "memory"); }
__device__ __forceinline__ uint64_t make_desc(uint32_t addr, uint32_t lbo, uint32_t sbo, uint32_t mode) {
    return (uint64_t)((addr & 0x3FFFF) >> 4) | ((uint64_t)(lbo >> 4) << 16) | ((uint64_t)(sbo >> 4) << 32) | ((uint64_t)mode << 62);
}
__device__ __forceinline__ void wgmma_rs128(float (&d)[64], uint2 hi, uint2 lo, uint64_t db, int acc) {
    asm volatile("{\n.reg .pred p;\nsetp.ne.b32 p, %69, 0;\nwgmma.mma_async.sync.aligned.m64n128k16.f32.bf16.bf16 {%0,%1,%2,%3,%4,%5,%6,%7,%8,%9,%10,%11,%12,%13,%14,%15,%16,%17,%18,%19,%20,%21,%22,%23,%24,%25,%26,%27,%28,%29,%30,%31,%32,%33,%34,%35,%36,%37,%38,%39,%40,%41,%42,%43,%44,%45,%46,%47,%48,%49,%50,%51,%52,%53,%54,%55,%56,%57,%58,%59,%60,%61,%62,%63}, {%64,%65,%66,%67}, %68, p, 1, 1, 0;\n}"
                 : "+f"(d[0]), "+f"(d[1]), "+f"(d[2]), "+f"(d[3]), "+f"(d[4]), "+f"(d[5]), "+f"(d[6]), "+f"(d[7]), "+f"(d[8]), "+f"(d[9]), "+f"(d[10]), "+f"(d[11]), "+f"(d[12]), "+f"(d[13]), "+f"(d[14]), "+f"(d[15]), "+f"(d[16]), "+f"(d[17]), "+f"(d[18]), "+f"(d[19]), "+f"(d[20]), "+f"(d[21]), "+f"(d[22]), "+f"(d[23]), "+f"(d[24]), "+f"(d[25]), "+f"(d[26]), "+f"(d[27]), "+f"(d[28]), "+f"(d[29]), "+f"(d[30]), "+f"(d[31]), "+f"(d[32]), "+f"(d[33]), "+f"(d[34]), "+f"(d[35]), "+f"(d[36]), "+f"(d[37]), "+f"(d[38]), "+f"(d[39]), "+f"(d[40]), "+f"(d[41]), "+f"(d[42]), "+f"(d[43]), "+f"(d[44]), "+f"(d[45]), "+f"(d[46]), "+f"(d[47]), "+f"(d[48]), "+f"(d[49]), "+f"(d[50]), "+f"(d[51]), "+f"(d[52]), "+f"(d[53]), "+f"(d[54]), "+f"(d[55]), "+f"(d[56]), "+f"(d[57]), "+f"(d[58]), "+f"(d[59]), "+f"(d[60]), "+f"(d[61]), "+f"(d[62]), "+f"(d[63])
                 : "r"(hi.x), "r"(hi.y), "r"(lo.x), "r"(lo.y), "l"(db), "r"(acc));
}
template <int V> struct Int { __device__ constexpr operator int() const { return V; } };
__device__ __forceinline__ void sts4(uint32_t a, const uint32_t* v) { asm volatile("st.shared.v4.u32 [%0], {%1,%2,%3,%4};" ::"r"(a), "r"(v[0]), "r"(v[1]), "r"(v[2]), "r"(v[3]) : "memory"); }
__device__ __forceinline__ uint32_t lds1(uint32_t a) { uint32_t v; asm volatile("ld.shared.u32 %0, [%1];" : "=r"(v) : "r"(a) : "memory"); return v; }
__device__ __forceinline__ uint4 lds4(uint32_t a) { uint4 v; asm volatile("ld.shared.v4.u32 {%0,%1,%2,%3}, [%4];" : "=r"(v.x), "=r"(v.y), "=r"(v.z), "=r"(v.w) : "r"(a) : "memory"); return v; }
__device__ __forceinline__ void cv_store(unsigned char* p, uint4 x, uint4 y) {
    asm volatile("st.relaxed.gpu.global.v2.u32 [%0], {%1,%2};" ::"l"(p), "r"(add2(x.x, __byte_perm(y.x, y.y, 0x5410))), "r"(add2(x.y, __byte_perm(y.z, y.w, 0x5410))) : "memory");
    asm volatile("st.relaxed.gpu.global.v2.u32 [%0], {%1,%2};" ::"l"(p + 128), "r"(add2(x.z, __byte_perm(y.x, y.y, 0x7632))), "r"(add2(x.w, __byte_perm(y.z, y.w, 0x7632))) : "memory");
}
__device__ __forceinline__ int usw(int ch) { return ch ^ ((ch >> 3) & 1); }
__global__ void __launch_bounds__(CV_THREADS, 1) conv_kernel(int layer, const uint4* __restrict__ piv, const float4* __restrict__ sum, const bf16* __restrict__ x1T,
                                                             bf16* __restrict__ dst, const uint4* __restrict__ tap, const __grid_constant__ CUtensorMap tmOut) {
    extern __shared__ __align__(1024) unsigned char sm[];
    SPAN(3 + 4 * layer, 0);
    bf16* Us = reinterpret_cast<bf16*>(sm + CV_SM_U);
    bf16* Xs = reinterpret_cast<bf16*>(sm + CV_SM_X);
#define CV_IDX int tid; asm volatile("mov.u32 %0, %tid.x;" : "=r"(tid)); const int lane = tid & 31, warp = __shfl_sync(~0u, tid >> 5, 0);
    const int d0 = blockIdx.x * CV_CPB, tile = blockIdx.x; (void)tile;
    const uint32_t cnt = smem_u32(sm + CV_SM_CNT);
    struct Lc { uint32_t a4, a8, uc, ud, y, e4, en, sp, ss; int go; };
    auto lane_consts = [&](int lane, int c) {
        const int mat = lane >> 3, r = lane & 7, g = lane >> 2, ti = lane & 3, e = g - 2 * ti;
        const int j2 = 13 + (r ^ 1) + 8 * (mat >> 1), j3 = j2 + 2, i0 = 8 * (mat & 1);
        const uint32_t sb = smem_u32(sm), oc = sb + usw(16 * (mat >> 1) + 2 * r + (mat & 1)) * 16;
        const Lc l = {sb + CV_SM_B + c * BX_LEN + ((j2 & 1) ? BX_3 + (4 * j2 + i0 + 84) * 2 : BX_5 + (4 * j2 + i0 + 80) * 2),
                      sb + CV_SM_B + c * BX_LEN + ((j3 & 1) ? BX_7 : BX_9) + (8 * j3 + i0 + 136) * 2,
                      oc + CV_SM_U + (c * ULEN + UPADF) * 2, sb + CV_SM_U + (c * ULEN + UPADF) * 2 + usw(16 * mat + 2 * r + 2) * 16, oc + CV_SM_Y + c * 8192,
                      sb + CV_SM_O + 2048 * c + (307 + 2 * g - ti) * 4, sb + CV_SM_T + c * TAPB + (152 + 144 + e) * 8 + 4,
                      e == -5 ? 0x4410u : e == -4 ? 0x1044u : 0x4444u, e == 3 ? 0x4410u : e == 4 ? 0x1044u : 0x4444u,
                      c * XCP * 2 + (lane >> 4) * 256 + (lane & 15) * 8};
        asm volatile("st.shared.u32 [%0], %1;" ::"r"(l.y), "r"(l.a4 ^ l.a8 ^ l.uc ^ l.ud ^ l.e4 ^ l.en ^ l.sp ^ l.ss ^ l.go) : "memory");
        return l;
    };
    unsigned char* const dq = reinterpret_cast<unsigned char*>(dst + (size_t)d0 * XCP);
    auto far = [&](auto T0_, const auto& seq, const Lc& lc, int c, int lane, const uint2 (&f)[20], uint32_t kk) {
        constexpr int T0 = T0_, T1 = T0 + 6, TC = T0 > 7 ? T0 : 7, NS = sizeof(seq) / sizeof(seq[0]), PD = T0 > 7 ? CV_PDH : CV_PDF;
        uint32_t bq[28], yw[4], yz[4], P, S;
        uint4 xv, yv;
        asm("prmt.b32 %0, %1, 0, %2;" : "=r"(P) : "r"(kk), "r"(lc.sp));
        asm("prmt.b32 %0, %1, 0, %2;" : "=r"(S) : "r"(kk), "r"(lc.ss));
#pragma unroll
        for (int k = 0; 2 * k < T1 - TC + 4; k++) ldsm_x4(bq + 4 * k, lc.uc + (TC - 8) * 256 + 512 * k);
#pragma unroll
        for (int k = 0; 4 * k < T1 - TC; k++) ldsm_x4(bq + 20 + 4 * k, lc.ud + (TC - 8) * 256 + 1024 * k);
        CST(3);
        mbar_wait(cnt + 8 * c, 0);
        mbar_wait(cnt + 40, 0);
        CST(4);
        float acc[6][4] = {};
        uint32_t a[PD + 1][4];
#pragma unroll
        for (int i = -PD; i < NS + 3; i++) {
            if (i + PD < NS) ldsm_x4_t(a[(i + PD) % (PD + 1)], seq[i + PD] < 32 ? lc.a4 + (seq[i + PD] - 2) * 128 : lc.a8 + (seq[i + PD] - 34) * 256);
            if (i < 0) continue;
#pragma unroll
            for (int T = T0; T < T1; T++) {
                if (i >= NS) break;
                const int ee = seq[i] < 32 ? 2 * T - 6 - seq[i] : T + 35 - seq[i];
                if (i == 0 && T >= TC) mma_bf16(acc[T - T0], P, 0u, S, P, bq[2 * (T - TC)], bq[2 * (T - TC) + 1]);
                if (i == 1 && T >= TC) mma_bf16_k8(acc[T - T0], 0u, S, bq[20 + T - TC]);
                if (i == (T >= TC ? 2 : 0)) mma_bf16(acc[T - T0], f[19].x, 0u, f[19].y, f[19].x, bq[2 * (T - TC + 4)], bq[2 * (T - TC + 4) + 1]);
                if (seq[i] < 32 ? ee >= 0 && ee <= 9 : ee >= 10) mma_bf16(acc[T - T0], a[i % (PD + 1)][0], a[i % (PD + 1)][1], a[i % (PD + 1)][2], a[i % (PD + 1)][3], f[ee].x, f[ee].y);
            }
#pragma unroll
            for (int k = 0; k < 3; k++) {
                const int o = 256 * T0 + 512 * k;
                auto at = [&](int d) { return i - d >= 0 && i - d < NS && seq[i - d < 0 ? 0 : i - d < NS ? i - d : 0] == 2 * T0 + 4 * k - 4; };
                if (at(CV_D2)) {
                    cv_store(dq + lc.go + o, xv, yv);
                    if (layer > 19 - 2 * k) __trap();
                }
                if (at(-2)) { ldsm_x4_t(yw, lc.y + o); ldsm_x4_t(yz, lc.y + 3584 + o); }
                if (at(1)) {
#pragma unroll
                    for (int q = 0; q < 4; q++) yw[q] = add2(add2(yw[q], yz[q]), pack2(acc[2 * k + (q >> 1)][2 * (q & 1)], acc[2 * k + (q >> 1)][2 * (q & 1) + 1]));
                    stsm_x4_t(lc.y + o, yw[0], yw[1], yw[2], yw[3]);
                    xv = lds4(smem_u32(Xs + c * XLEN) + o + lane * 16);
                    __syncwarp();
                    yv = lds4(smem_u32(sm + CV_SM_Y) + c * 8192 + o + usw(lane) * 16);
                    if (layer > 20 - 2 * k) __trap();
                    if (k == 2) CST(6);
                }
            }
        }
    };
    TSTAMP1X(9, 256);
    if (threadIdx.x >= 256) {
        CV_IDX
        const int t2 = tid - 256, wgu = (warp >> 2) & 1, g = lane >> 2, ti = lane & 3;
        if (t2 == 0) {
            mbar_init(cnt + 48, 1);
            asm volatile("fence.mbarrier_init.release.cluster;" ::: "memory");
            mbar_expect_tx(cnt + 48, CV_CPB * 2048);
            bulk_load(smem_u32(sm + CV_SM_O), tap + d0 * 128, CV_CPB * 2048, cnt + 48);
        } else if (lane == 0) {
            if (warp < 15) mbar_init(cnt + 8 * (warp - 9), warp == 14 ? 8 : 4);
            else if (layer) prefetch_tmap(&tmOut);
        }
        if (t2 < 140) {
            const int k = t2;
            const int off = k < 20 ? CV_SM_B + BX_5 + 8 * k : k < 40 ? CV_SM_B + BX_3 + 8 * (k - 20) : k < 74 ? CV_SM_B + BX_9 + 8 * (k - 40) : k < 108 ? CV_SM_B + BX_7 + 8 * (k - 74) : CV_SM_U + 8 * (k - 108);
            const int str = k < 108 ? BX_LEN : ULEN * 2;
#pragma unroll
            for (int c = 0; c < CV_CPB; c++) *reinterpret_cast<uint2*>(sm + off + c * str) = make_uint2(0, 0);
        }
        fence_async_smem();
        asm volatile("bar.arrive 3, 512;" ::: "memory");
        asm volatile("bar.sync 1, 256;" ::: "memory");
        TSTAMP1X(10, 256);
        asm volatile("setmaxnreg.inc.sync.aligned.u32 168;");
        const int hc = wgu ? warp & 3 : 4;
        const Lc lc = lane_consts(lane, hc);
        const uint32_t* E2[3];
#pragma unroll
        for (int k = 0; k < 3; k++) {
            const int i = min(t2 + 256 * k, 759), h = i / 76;
            E2[k] = reinterpret_cast<const uint32_t*>(sm + CV_SM_O) + 3 + i + (h >> 1) * 360 + (h & 1) * 52;
        }
        mbar_wait(cnt + 48, 0);
        TSTAMP1X(11, 256);
        {
            uint32_t w[3][4];
#pragma unroll
            for (int k = 0; k < 3; k++) { w[k][0] = E2[k][0]; w[k][1] = E2[k][1]; w[k][2] = E2[k][64]; w[k][3] = E2[k][65]; }
#pragma unroll
            for (int k = 0; k < 3; k++)
                *reinterpret_cast<uint4*>(sm + CV_SM_T + min(t2 + 256 * k, 759) * 16) =
                    make_uint4(__byte_perm(w[k][1], w[k][0], 0x7610), __byte_perm(w[k][3], w[k][2], 0x7610), __byte_perm(w[k][1], 0, 0x1032), __byte_perm(w[k][3], 0, 0x1032));
        }
        asm volatile("bar.sync 1, 256;" ::: "memory");
        const uint2* Tc = reinterpret_cast<const uint2*>(sm + CV_SM_T) + 16 + 76 * (warp & 2) + 8 * (warp & 1) + g - 2 * ti;
        uint2 fa[8][2], fn[8][2];
        auto near_taps = [&](uint2 (&f)[8][2], int c) {
#pragma unroll
            for (int m = 0; m < 8; m++) { f[m][0] = Tc[c * (TAPB / 8) + 16 * m]; f[m][1] = Tc[c * (TAPB / 8) + 16 * m - 8]; }
        };
        near_taps(fa, 3 * wgu);
        near_taps(fn, 2 - wgu);
        TSTAMP1X(12, 256); CST(0);
        uint32_t ya = smem_u32(sm + CV_SM_Y) + wgu * 8192 + (warp & 2) * 2048 + usw(2 * lane + (warp & 1)) * 16;
        uint64_t db = make_desc(smem_u32(Us + wgu * ULEN + UPADF), 16, 256, 3);
        if (wgu) asm volatile("bar.sync 6, 384;" ::: "memory");
        int c = wgu;
        auto chain = [&](const uint2 (&f)[8][2], auto&& meanwhile) {
            float acc[64];
            asm volatile("bar.sync %0, %1;" ::"r"(c ? 4 + wgu : 2), "r"(c ? 256 : 384) : "memory");
            TSTAMPC(1 + 3 * c);
            wgmma_fence();
#pragma unroll
            for (int m = 0; m < 8; m++) {
                wgmma_rs128(acc, f[m][0], f[m][1], db - (uint64_t)(2 * m), m);
                if (m == CV_HAND && c < 4) asm volatile("bar.arrive %0, 256;" ::"r"(5 - wgu) : "memory");
            }
            wgmma_commit();
            asm volatile("griddepcontrol.launch_dependents;" ::: "memory");
            TSTAMPC(2 + 3 * c); CST(13 + (c >> 1));
            meanwhile();
            wgmma_wait<0>();
            TSTAMPC(3 + 3 * c); CST(10 + (c >> 1));
            uint32_t w[16];
#pragma unroll
            for (int j = 0; j < 16; j++) w[j] = j ? pack2(acc[4 * j] + acc[4 * j - 2], acc[4 * j + 1] + acc[4 * j - 1]) : pack2(acc[0], acc[1]);
#pragma unroll
            for (int j = 0; j < 16; j += 4) stsm_x4_t(ya + 256 * j, w[j], w[j + 1], w[j + 2], w[j + 3]);
            __syncwarp();
            if (lane == 0) mbar_arrive(cnt + 8 * c);
            c += 2; ya += 16384; db += ULEN / 4;
        };
        const uint32_t e4 = lc.e4, e8 = e4 + 428 - 4 * g;
        uint2 fl[4];
        uint32_t kk;
#pragma unroll 1
        for (;;) {
            if (c != 1) chain(fa, [&] {
                if (c == 3 || warp + c == 12) {
#pragma unroll
                    for (int k = 0; k < 19; k++) (k < 16 ? fn[(k >> 1) & 7][k & 1] : fl[k & 3]) = make_uint2(lds1(k < 10 ? e4 + 32 * k + 16 : e8 + 32 * k - 304), lds1(k < 10 ? e4 + 32 * k : e8 + 32 * k - 320));
                    fl[3] = make_uint2(lds1(lc.en), lds1(lc.en - 64));
                    kk = lds1(smem_u32(sm + CV_SM_O) + 2048 * hc + 1672);
                }
            });
            if (c > 4) break;
            if (c == 2) asm volatile("bar.sync 7, 384;" ::: "memory");
            chain(fn, [&] { if (c == 2) near_taps(fa, 4); });
        }
        TSTAMP1X(6, 256); CST(2);
        if (wgu || warp == 8) {
            constexpr int seq[29] = {5, 6, 32, 7, 33, 8, 34, 9, 35, 10, 36, 11, 12, 13, 14, 15, 16, 17, 37, 18, 38, 19, 20, 21, 39, 22, 40, 23, 24};
            uint2 f[20];
#pragma unroll
            for (int k = 0; k < 20; k++) f[k] = k < 16 ? fn[(k >> 1) & 7][k & 1] : fl[k & 3];
            far(Int<10>(), seq, lc, hc, lane, f, kk);
        }
    } else {
        asm volatile("setmaxnreg.dec.sync.aligned.u32 88;");
        CV_IDX
        const uint4* ppv = piv + tid;
        const float4* psv = sum + tid;
        const uint2* pxv = reinterpret_cast<const uint2*>(x1T + (size_t)d0 * XCP) + (tid >> 4) * 32 + (tid & 15);
        asm volatile("st.shared.u64 [%0], %1;" ::"r"(smem_u32(Xs) + tid * 16), "l"((uint64_t)ppv ^ (uint64_t)psv ^ (uint64_t)pxv) : "memory");
        const int tc = (0x04302100 >> (4 * warp)) & 7;
        const Lc lc = lane_consts(lane, tc);
        pdl_sync();
        SPAN(3 + 4 * layer, 1);
        TSTAMP(0); CST(0);
        if (tid == 0) TSTAMPC(0);
        if (threadIdx.x == 0) { GSTAMP(g_tim, 15); }
        float4 sv[4];
#pragma unroll
        for (int k = 0; k < 4; k++)
            asm volatile("ld.relaxed.gpu.global.v4.f32 {%0,%1,%2,%3}, [%4];" : "=f"(sv[k].x), "=f"(sv[k].y), "=f"(sv[k].z), "=f"(sv[k].w) : "l"(psv + 256 * k) : "memory");
        uint4 pv;
        asm volatile("ld.relaxed.gpu.global.v4.u32 {%0,%1,%2,%3}, [%4];" : "=r"(pv.x), "=r"(pv.y), "=r"(pv.z), "=r"(pv.w) : "l"(ppv) : "memory");
        uint2 xe[CV_CPB], xo[CV_CPB];
#pragma unroll
        for (int c = 0; c < CV_CPB; c++) {
            asm volatile("ld.relaxed.gpu.global.v2.u32 {%0,%1}, [%2];" : "=r"(xe[c].x), "=r"(xe[c].y) : "l"(pxv + c * (XCP / 4)) : "memory");
            asm volatile("ld.relaxed.gpu.global.v2.u32 {%0,%1}, [%2];" : "=r"(xo[c].x), "=r"(xo[c].y) : "l"(pxv + c * (XCP / 4) + 16) : "memory");
        }
        constexpr float idm = 1.0f / DM;
        uint32_t mw[4];
        float rs[8];
#pragma unroll
        for (int k = 0; k < 4; k++) {
            const uint32_t pw = k == 0 ? pv.x : k == 1 ? pv.y : k == 2 ? pv.z : pv.w;
            const float d0_ = sv[k].x * idm, d1_ = sv[k].z * idm;
            mw[k] = pack2(__uint_as_float(pw << 16) + d0_, __uint_as_float(pw & 0xffff0000u) + d1_);
            const uint32_t vr = pack2(fmaxf(fmaf(-d0_, d0_, sv[k].y * idm), 0.f), fmaxf(fmaf(-d1_, d1_, sv[k].w * idm), 0.f));
            const uint32_t ve = pack2(__uint_as_float(vr << 16) + 1e-5f, __uint_as_float(vr & 0xffff0000u) + 1e-5f);
            const uint32_t sd = pack2(sqrt_apx(__uint_as_float(ve << 16)), sqrt_apx(__uint_as_float(ve & 0xffff0000u)));
            rs[2 * k] = rcp_apx(__uint_as_float(sd << 16)); rs[2 * k + 1] = rcp_apx(__uint_as_float(sd & 0xffff0000u));
        }
        if (rs[0] != 123.f) TSTAMP(13);
        const uint32_t ua = smem_u32(Us) + usw(tid + UPADF / 8) * 16;
        uint32_t uw[CV_CPB][4];
#pragma unroll
        for (int c = 0; c < CV_CPB; c++) {
            const uint32_t e0 = sub2(xe[c].x, mw[0]), e1 = sub2(xe[c].y, mw[1]), o0 = sub2(xo[c].x, mw[2]), o1 = sub2(xo[c].y, mw[3]);
            uw[c][0] = pack2(__uint_as_float(e0 << 16) * rs[0], __uint_as_float(o0 << 16) * rs[4]); uw[c][1] = pack2(__uint_as_float(e0 & 0xffff0000u) * rs[1], __uint_as_float(o0 & 0xffff0000u) * rs[5]);
            uw[c][2] = pack2(__uint_as_float(e1 << 16) * rs[2], __uint_as_float(o1 << 16) * rs[6]); uw[c][3] = pack2(__uint_as_float(e1 & 0xffff0000u) * rs[3], __uint_as_float(o1 & 0xffff0000u) * rs[7]);
            asm volatile("st.shared.v4.u32 [%0], {%1,%2,%3,%4};" ::"r"(ua + c * ULEN * 2), "r"(uw[c][0]), "r"(uw[c][1]), "r"(uw[c][2]), "r"(uw[c][3]) : "memory");
            if (c < 2) {
                fence_async_smem();
                asm volatile("bar.arrive %0, 384;" ::"r"(2 + 4 * c) : "memory");
                if (layer > 29 - c) __trap();
            }
        }
        fence_async_smem();
#pragma unroll
        for (int c = 0; c < CV_CPB; c++) *reinterpret_cast<uint4*>(Xs + c * XLEN + tid * 8) = make_uint4(xe[c].x, xe[c].y, xo[c].x, xo[c].y);
        asm volatile("bar.arrive 7, 384;" ::: "memory");
        asm volatile("bar.sync 3, 512;" ::: "memory");
        TSTAMP(1); CST(1);
        {
            auto box = [&](auto c0, auto c1, int chunk, int cb, bool full) {
                const uint32_t ea = smem_u32(Us + cb * ULEN) + usw(chunk + UPADF / 8 + (lane ? 1 : -1)) * 16, bx = smem_u32(sm + CV_SM_B + cb * BX_LEN) + chunk * 16;
                uint32_t lo[CV_CPB][4], hi[CV_CPB][2];
#pragma unroll
                for (int c = c0; c < c1; c++) {
                    lo[c][0] = 0;
#pragma unroll
                    for (int k = 1; k < 4; k++) lo[c][k] = __shfl_up_sync(~0u, uw[c][k], 1);
#pragma unroll
                    for (int k = 0; k < 2; k++) hi[c][k] = __shfl_down_sync(~0u, uw[c][k], 1);
                }
#pragma unroll
                for (int c = c0; c < c1; c++)
                    asm volatile("{\n.reg .pred p, q;\nsetp.eq.s32 p, %7, 0;\nsetp.eq.s32 q, %7, 31;\n@p ld.shared.v4.u32 {%0,%1,%2,%3}, [%6];\n@q ld.shared.v2.u32 {%4,%5}, [%6];\n}"
                                 : "+r"(lo[c][0]), "+r"(lo[c][1]), "+r"(lo[c][2]), "+r"(lo[c][3]), "+r"(hi[c][0]), "+r"(hi[c][1]) : "r"(ea + c * ULEN * 2), "r"(lane) : "memory");
#pragma unroll
                for (int c = c0; c < c1; c++) {
                    const uint32_t e[9] = {lo[c][1], lo[c][2], lo[c][3], uw[c][0], uw[c][1], uw[c][2], uw[c][3], hi[c][0], hi[c][1]};
                    uint32_t o[8], p[8], t[7], b3[5], b5[7];
#pragma unroll
                    for (int i = 0; i < 8; i++) { o[i] = __byte_perm(e[i], e[i + 1], 0x5432); p[i] = add2(e[i], o[i]); }
#pragma unroll
                    for (int i = 0; i < 5; i++) b3[i] = add2(o[i], p[i + 1]);
                    sts4(bx + c * BX_LEN + BX_3 + 160, b3);
#pragma unroll
                    for (int i = 1; i < 7; i++) { t[i] = add2(p[i], p[i + 1]); b5[i] = add2(t[i], e[i + 2]); }
                    sts4(bx + c * BX_LEN + BX_5 + 160, b5 + 2);
                    if (full) {
#pragma unroll
                        for (int i = 1; i < 5; i++) { b3[i] = add2(b3[i], t[i + 2]); t[i] = add2(t[i], b5[i + 2]); }
                        sts4(bx + c * BX_LEN + BX_7 + 272, b3 + 1);
                        sts4(bx + c * BX_LEN + BX_9 + 272, t + 1);
                    }
                }
            };
            auto reload = [&](int c, uint32_t a) { const uint4 v = lds4(a); uw[c][0] = v.x; uw[c][1] = v.y; uw[c][2] = v.z; uw[c][3] = v.w; };
            if (warp >= 6) {
#pragma unroll
                for (int c = 0; c < 3; c++) reload(c, ua - 1024 + (c + 2) * ULEN * 2);
            }
            if (warp >= 4) {
#pragma unroll
                for (int c = 3; c < 5; c++) reload(c, ua - 2048 + c * ULEN * 2);
            }
            box(Int<0>(), Int<3>(), warp < 6 ? tid : tid - 64, warp < 6 ? 0 : 2, warp < 4);
            if (warp >= 4) box(Int<3>(), Int<5>(), tid - 128, 0, true);
            else if (tid >= 128 - CV_CPB) {
                const int c = 127 - tid;
                const uint2 v = *reinterpret_cast<const uint2*>(Us + c * ULEN + UPADF);
                const float s1 = __uint_as_float(v.x << 16), s2 = s1 + __uint_as_float(v.x & 0xffff0000u), s3 = s2 + __uint_as_float(v.y << 16), s4 = s3 + __uint_as_float(v.y & 0xffff0000u);
                unsigned char* bc = sm + CV_SM_B + c * BX_LEN;
                *reinterpret_cast<uint32_t*>(bc + BX_5 + 156) = pack2(s1, s2);
                *reinterpret_cast<uint2*>(bc + BX_7 + 264) = make_uint2(v.x << 16, pack2(s2, s3));
                *reinterpret_cast<uint2*>(bc + BX_9 + 264) = make_uint2(pack2(s1, s2), pack2(s3, s4));
            }
        }
        __syncwarp();
        if (lane == 0) mbar_arrive(cnt + 40);
        TSTAMP(2); CST(2);
        if (layer && blockIdx.x == 0 && tid == 224) g_epoch = ld_epoch();
        __syncwarp();
        if ((0x6e >> warp) & 1) {
            constexpr int seq[16] = {0, 1, 2, 3, 4, 5, 6, 32, 7, 8, 9, 33, 10, 34, 11, 12};
            uint2 f[20];
            mbar_wait(cnt, 0);
            const uint32_t e8 = lc.e4 + 428 - (lane & 28);
#pragma unroll
            for (int k = 0; k < 13; k++) f[k] = make_uint2(lds1(k < 10 ? lc.e4 + 32 * k + 16 : e8 + 32 * k - 304), lds1(k < 10 ? lc.e4 + 32 * k : e8 + 32 * k - 320));
            f[19] = make_uint2(lds1(lc.en), lds1(lc.en - 64));
            far(Int<4>(), seq, lc, tc, lane, f, lds1(smem_u32(sm + CV_SM_O) + 2048 * tc + 1672));
        }
    }
    {
        CV_IDX
        if ((0xc91 >> warp) & 1) {
            const int c = __popc(0xc91 & ((1 << warp) - 1));
            uint4 xv[2], yv[2];
#pragma unroll
            for (int k = 0; k < 2; k++) xv[k] = lds4(smem_u32(Xs + c * XLEN) + 512 * k + lane * 16);
            const uint32_t u0 = lds1(smem_u32(Us + c * ULEN) + (lane == 31 ? UPADF * 2 : 0));
            mbar_wait(cnt + 8 * c, 0);
#pragma unroll
            for (int k = 0; k < 2; k++) yv[k] = lds4(smem_u32(sm + CV_SM_Y) + c * 8192 + 512 * k + usw(lane) * 16);
            const uint4 yz = lds4(smem_u32(sm + CV_SM_Y) + c * 8192 + 4096 + usw(lane) * 16);
            const float kk = __uint_as_float(lds1(smem_u32(sm + CV_SM_O) + 2048 * c + 1272) << 16);
            yv[1].x = add2(yv[1].x, yz.x); yv[1].y = add2(yv[1].y, yz.y); yv[1].z = add2(yv[1].z, yz.z);
            yv[1].w = pack2(fmaf(kk, __uint_as_float(u0 << 16), __uint_as_float(yv[1].w << 16) + __uint_as_float(yz.w << 16)),
                            fmaf(kk, __uint_as_float(u0 << 16) + __uint_as_float(u0 & 0xffff0000u), __uint_as_float(yv[1].w & 0xffff0000u) + __uint_as_float(yz.w & 0xffff0000u)));
#pragma unroll
            for (int k = 0; k < 2; k++) cv_store(dq + c * XCP * 2 + (lane >> 4) * 256 + (lane & 15) * 8 + 512 * k, xv[k], yv[k]);
        }
        TSTAMP(4); CST(8);
        if (layer == 1) {
            const int mb = blockIdx.x >> 3, cg = blockIdx.x & 7;
            const bf16* src = dst + (size_t)(cg * 80 + (tid >> 4)) * XCP + mb * 128 + (tid & 15) * 8;
            uint32_t v[3][4];
            __syncthreads();
            uint32_t todo = warp < 8 ? 7 : 3;
#pragma unroll 1
            for (int it = 0; it < SPIN_MAX; it++) {
#pragma unroll
                for (int k = 0; k < 3; k++)
                    if (todo >> k & 1)
                        asm volatile("ld.relaxed.gpu.global.v4.u32 {%0,%1,%2,%3}, [%4];" : "=r"(v[k][0]), "=r"(v[k][1]), "=r"(v[k][2]), "=r"(v[k][3]) : "l"(src + k * (32 * XCP)) : "memory");
#pragma unroll
                for (int k = 0; k < 3; k++)
                    if ((todo >> k & 1) && v[k][0] != ~0u && v[k][1] != ~0u && v[k][2] != ~0u && v[k][3] != ~0u) {
                        *reinterpret_cast<uint4*>(sm + (32 * k + (tid >> 4)) * 272 + (tid & 15) * 16) = make_uint4(v[k][0], v[k][1], v[k][2], v[k][3]);
                        todo ^= 1u << k;
                    }
                if (!todo) break;
                __nanosleep(CV_SLEEP);
            }
            __syncthreads();
            uint32_t w[12];
#pragma unroll
            for (int k = 0; k < 3; k++) ldsm_x4(&w[4 * k], smem_u32(sm) + min(32 * k + lane, 79) * 272 + warp * 16);
            const uint32_t ot = smem_u32(sm + CV_SM_O) + warp * 1280, oa = ot + (lane & 7) * 160 + (lane >> 3) * 16;
            stsm_x4_t(oa, w[0], w[1], w[2], w[3]);
            stsm_x4_t(oa + 64, w[4], w[5], w[6], w[7]);
            asm volatile("stmatrix.sync.aligned.m8n8.x2.trans.shared.b16 [%0], {%1,%2};" ::"r"(oa + 128), "r"(w[8]), "r"(w[9]) : "memory");
            fence_async_smem();
            __syncwarp();
            if (lane == 0) {
                asm volatile("cp.async.bulk.tensor.3d.global.shared::cta.bulk_group [%0, {%1, %2, %3}], [%4];" ::"l"(&tmOut), "r"(cg * 80), "r"(mb * 64 + 8 * (warp & 7)), "r"(warp >> 3), "r"(ot) : "memory");
                asm volatile("cp.async.bulk.commit_group;" ::: "memory");
                asm volatile("cp.async.bulk.wait_group.read 0;" ::: "memory");
            }
        }
    }
    TSTAMP(3); CST(9); CST_END;
    GSTAMP(g_tim, 14);
    SPAN(3 + 4 * layer, 3);
}

template <int TA, int TB>
__device__ __forceinline__ void wgmma_n240(float (&d)[120], uint64_t da, uint64_t db, int acc) {
    asm volatile("{\n.reg .pred p;\nsetp.ne.b32 p, %124, 0;\nwgmma.mma_async.sync.aligned.m64n240k16.f32.bf16.bf16 {%0,%1,%2,%3,%4,%5,%6,%7,%8,%9,%10,%11,%12,%13,%14,%15,%16,%17,%18,%19,%20,%21,%22,%23,%24,%25,%26,%27,%28,%29,%30,%31,%32,%33,%34,%35,%36,%37,%38,%39,%40,%41,%42,%43,%44,%45,%46,%47,%48,%49,%50,%51,%52,%53,%54,%55,%56,%57,%58,%59,%60,%61,%62,%63,%64,%65,%66,%67,%68,%69,%70,%71,%72,%73,%74,%75,%76,%77,%78,%79,%80,%81,%82,%83,%84,%85,%86,%87,%88,%89,%90,%91,%92,%93,%94,%95,%96,%97,%98,%99,%100,%101,%102,%103,%104,%105,%106,%107,%108,%109,%110,%111,%112,%113,%114,%115,%116,%117,%118,%119}, %120, %121, p, 1, 1, %122, %123;\n}"
                 : "+f"(d[0]), "+f"(d[1]), "+f"(d[2]), "+f"(d[3]), "+f"(d[4]), "+f"(d[5]), "+f"(d[6]), "+f"(d[7]), "+f"(d[8]), "+f"(d[9]), "+f"(d[10]), "+f"(d[11]), "+f"(d[12]), "+f"(d[13]), "+f"(d[14]), "+f"(d[15]), "+f"(d[16]), "+f"(d[17]), "+f"(d[18]), "+f"(d[19]), "+f"(d[20]), "+f"(d[21]), "+f"(d[22]), "+f"(d[23]), "+f"(d[24]), "+f"(d[25]), "+f"(d[26]), "+f"(d[27]), "+f"(d[28]), "+f"(d[29]), "+f"(d[30]), "+f"(d[31]), "+f"(d[32]), "+f"(d[33]), "+f"(d[34]), "+f"(d[35]), "+f"(d[36]), "+f"(d[37]), "+f"(d[38]), "+f"(d[39]), "+f"(d[40]), "+f"(d[41]), "+f"(d[42]), "+f"(d[43]), "+f"(d[44]), "+f"(d[45]), "+f"(d[46]), "+f"(d[47]), "+f"(d[48]), "+f"(d[49]), "+f"(d[50]), "+f"(d[51]), "+f"(d[52]), "+f"(d[53]), "+f"(d[54]), "+f"(d[55]), "+f"(d[56]), "+f"(d[57]), "+f"(d[58]), "+f"(d[59]), "+f"(d[60]), "+f"(d[61]), "+f"(d[62]), "+f"(d[63]), "+f"(d[64]), "+f"(d[65]), "+f"(d[66]), "+f"(d[67]), "+f"(d[68]), "+f"(d[69]), "+f"(d[70]), "+f"(d[71]), "+f"(d[72]), "+f"(d[73]), "+f"(d[74]), "+f"(d[75]), "+f"(d[76]), "+f"(d[77]), "+f"(d[78]), "+f"(d[79]), "+f"(d[80]), "+f"(d[81]), "+f"(d[82]), "+f"(d[83]), "+f"(d[84]), "+f"(d[85]), "+f"(d[86]), "+f"(d[87]), "+f"(d[88]), "+f"(d[89]), "+f"(d[90]), "+f"(d[91]), "+f"(d[92]), "+f"(d[93]), "+f"(d[94]), "+f"(d[95]), "+f"(d[96]), "+f"(d[97]), "+f"(d[98]), "+f"(d[99]), "+f"(d[100]), "+f"(d[101]), "+f"(d[102]), "+f"(d[103]), "+f"(d[104]), "+f"(d[105]), "+f"(d[106]), "+f"(d[107]), "+f"(d[108]), "+f"(d[109]), "+f"(d[110]), "+f"(d[111]), "+f"(d[112]), "+f"(d[113]), "+f"(d[114]), "+f"(d[115]), "+f"(d[116]), "+f"(d[117]), "+f"(d[118]), "+f"(d[119])
                 : "l"(da), "l"(db), "n"(TA), "n"(TB), "r"(acc));
}

__device__ __forceinline__ void wgmma_n80(float (&d)[40], uint64_t da, uint64_t db, int acc) {
    asm volatile("{\n.reg .pred p;\nsetp.ne.b32 p, %42, 0;\nwgmma.mma_async.sync.aligned.m64n80k16.f32.bf16.bf16 {%0,%1,%2,%3,%4,%5,%6,%7,%8,%9,%10,%11,%12,%13,%14,%15,%16,%17,%18,%19,%20,%21,%22,%23,%24,%25,%26,%27,%28,%29,%30,%31,%32,%33,%34,%35,%36,%37,%38,%39}, %40, %41, p, 1, 1, 0, 1;\n}"
                 : "+f"(d[0]), "+f"(d[1]), "+f"(d[2]), "+f"(d[3]), "+f"(d[4]), "+f"(d[5]), "+f"(d[6]), "+f"(d[7]), "+f"(d[8]), "+f"(d[9]), "+f"(d[10]), "+f"(d[11]), "+f"(d[12]), "+f"(d[13]), "+f"(d[14]), "+f"(d[15]), "+f"(d[16]), "+f"(d[17]), "+f"(d[18]), "+f"(d[19]), "+f"(d[20]), "+f"(d[21]), "+f"(d[22]), "+f"(d[23]), "+f"(d[24]), "+f"(d[25]), "+f"(d[26]), "+f"(d[27]), "+f"(d[28]), "+f"(d[29]), "+f"(d[30]), "+f"(d[31]), "+f"(d[32]), "+f"(d[33]), "+f"(d[34]), "+f"(d[35]), "+f"(d[36]), "+f"(d[37]), "+f"(d[38]), "+f"(d[39])
                 : "l"(da), "l"(db), "r"(acc));
}

constexpr int A1_THREADS = 384;
constexpr int A1_NST = 4;
#define A1_SKEW 8
constexpr int A1_STAGE = 16384 + WQ_STAGE;
constexpr int A1_KVP = 336;
constexpr int A1_SM_KV = 2 * A1_STAGE;
constexpr int A1_SM_BAR = A1_NST * A1_STAGE;
constexpr int A1_SM_RS = A1_SM_BAR + 512;
constexpr int A1_SM_W0 = A1_SM_BAR + 3072, A1_SM_W3 = A1_SM_BAR - 3 * WOB, A1_SM_A1 = 2 * WOB, A1_SM_A0 = A1_SM_A1 + 61440;
constexpr int A1_SM_XA = A1_SM_W0 + 2 * WOB, A1_SM_XB = A1_SM_XA + 2048;
constexpr int A1_SMEM = A1_SM_W0 + 3 * WOB;
static_assert(A1_SM_W3 >= A1_SM_KV + 144 * A1_KVP && A1_SM_W3 % 512 == 0 && A1_SM_A1 % 1024 == 0 && A1_SM_A0 <= A1_SM_KV && A1_SM_A0 + 61440 <= A1_SM_W3 && A1_SMEM <= 232448, "layout");
__device__ __forceinline__ constexpr uint32_t wo_off(int h) { return h * WOB + (h < 3 ? A1_SM_W0 : h < 6 ? A1_SM_W3 - 3 * WOB : -6 * WOB); }
#define A1_FRED "red.relaxed.gpu.global.add.u32"
#define A1_FLD "ld.acquire.gpu.global.u32"
#define ST_SLEEP 20
#define ST_SLEEP0 300
#define WO_LATE bar_done
#define A1_P0 2
#define A1_PW (kb - 2)
#define A1_FSPIN SPIN_MAX
#define A1_FSLEEP 40
#define YT_LAYER 1
#define WOT 352
#define A1_WOAT 6

template <int L>
__device__ __forceinline__ void a1_mainloop(float (&acc)[120], uint32_t sbase, uint32_t bars, int wg, int tile) {
    constexpr int layer = L; (void)layer;
    const uint64_t da0 = L ? make_desc(sbase + wg * 8192, 8192, 1024, 1) : make_desc(sbase + wg * 8192, 16, 1024, 1), db0 = make_desc(sbase + 16384, 1024, 256, 3);
#pragma unroll 1
    for (int t = 0;; t++) {
        const int st = t % A1_NST;
        mbar_wait(bars + 8 * st, (t / A1_NST) & 1);
        if (t == A1_SKEW && wg == 0) mbar_wait(bars + 160, 0);
        TSTAMP3(1 + t);
        wgmma_fence();
#pragma unroll
        for (int kk = 0; kk < 4; kk++) wgmma_n240<L, 1>(acc, da0 + (uint32_t)(st * (A1_STAGE / 16) + kk * (L ? 128 : 2)), db0 + (uint32_t)(st * (A1_STAGE / 16) + (kk >> 1) * (WQ_STAGE / 32) + (kk & 1) * 32), kk ? 1 : t);
        wgmma_commit();
        if (t == 9) break;
        if (t == A1_SKEW - 1 && wg == 0) wgmma_wait<0>(); else wgmma_wait<1>();
        if (t > 0 && (threadIdx.x & 127) == 0) {
            if (t != A1_SKEW || wg) mbar_arrive(bars + 8 * (A1_NST + (t - 1) % A1_NST));
            if (t == A1_SKEW - 1 && wg == 0) mbar_arrive(bars + 8 * (A1_NST + t % A1_NST));
        }
    }
}

__global__ void __launch_bounds__(A1_THREADS, 1) a1_kernel(const int layer, const bf16* __restrict__ x0, const unsigned char* __restrict__ wq, const unsigned char* __restrict__ wo,
                                                           float2* __restrict__ rsum, uint4* __restrict__ of, const __grid_constant__ CUtensorMap tmX,
                                                           const __grid_constant__ CUtensorMap tmR, const __grid_constant__ CUtensorMap tmX1, const __grid_constant__ TileTab tab) {
    extern __shared__ __align__(1024) unsigned char stg[];
    const uint32_t sbase = smem_u32(stg);
    const uint32_t bars = sbase + A1_SM_BAR;
    const uint32_t bar_stat = bars + 64, bar_kv = bars + 72, bar_rd = bars + 168;
    const uint32_t bar_wo = bars + 208, bar_done = bars + 216, bar_pv = bars + 224, bar_kvf = bars + 232, bar_f2 = bars + 248, bar_e2 = bars + 384, que = bars + 448;
    const int tid = threadIdx.x;
    const int w = __shfl_sync(~0u, tid >> 5, 0), wg = w >> 2;
    uint32_t smid, ns;
    asm volatile("mov.u32 %0, %smid;" : "=r"(smid));
    asm volatile("mov.u32 %0, %nsmid;" : "=r"(ns));
    const auto te = tab.e[ns == tab.ns ? smid : 132 + blockIdx.x];
    const int tile = te.tile, mb = te.mb, hg = te.hg;
    float2* rst = reinterpret_cast<float2*>(stg + A1_SM_RS) + 8;
    auto issue_w = [&](int it) { bulk_load(sbase + (it % A1_NST) * A1_STAGE + 16384, wq + te.woff + it * WQ_STAGE, WQ_STAGE, bars + 8 * (it % A1_NST)); };
    auto issue_x = [&](int it, int kb) {
        asm volatile("cp.async.bulk.tensor.5d.shared::cluster.global.mbarrier::complete_tx::bytes [%0], [%1, {%3, %3, %3, %4, %5}], [%2];"
                     ::"r"(sbase + (it % A1_NST) * A1_STAGE), "l"(&tmX), "r"(bars + 8 * (it % A1_NST)), "r"(0), "r"(mb), "r"(kb) : "memory");
    };
    if (w == 8 && tile < 128) {
        const bool one = elect();
        if (one) {
#pragma unroll
            for (int i = 0; i < A1_NST; i++) mbar_init(bars + 8 * i, 1);
            asm volatile("fence.mbarrier_init.release.cluster;" ::: "memory");
        }
        __syncwarp();
        asm volatile("bar.arrive 0, 384;" ::: "memory");
        if (one) {
#define PW asm volatile("griddepcontrol.wait;" ::: "memory");
            if (layer) { issue_w(0); PW issue_x(0, te.kb0); issue_x(1, te.kb0 + 1); }
            else { issue_x(0, te.kb0); issue_x(1, te.kb0 + 1); PW issue_w(0); }
            issue_w(1);
#pragma unroll
            for (int i = 0; i < A1_NST; i++) mbar_expect_tx(bars + 8 * i, A1_STAGE);
            asm volatile("griddepcontrol.launch_dependents;" ::: "memory");
#pragma unroll
            for (int kb = 2; kb < A1_P0; kb++) { issue_x(kb, te.kb0 + kb); issue_w(kb); }
            DBGC(34); DBGV(33, smid); DBGV(40, t_entry); DBGV(30, t_a); DBGV(31, t_b); DBGV(32, t_c); DBGV(38, t_d); DBGV(39, t_e);
        }
    }
    if (tile >= 128) { sm_idle(layer); return; }
    if (wg == 2) {
        if (w != 8) {
            if (tid == 320) { prefetch_tmap(&tmX); prefetch_tmap(&tmR); prefetch_tmap(&tmX1); }
            asm volatile("bar.sync 0, 384;" ::: "memory");
        }
        if (w == 9) {
            asm volatile("bar.arrive 3, 64;" ::: "memory");
            if (layer == 0) pdl_sync();
            float4 a[2] = {};
#pragma unroll
            for (int k = 0; k < 10; k++)
#pragma unroll
                for (int h = 0; h < 2; h++) {
                    const int c4 = min(tid - 288 + 32 * h, 59);
                    const float4 v = __ldcg(reinterpret_cast<const float4*>(g_csp + k * 1920 + hg * 80) + c4 + (c4 / 20) * 140);
                    a[h].x += v.x; a[h].y += v.y; a[h].z += v.z; a[h].w += v.w;
                }
#pragma unroll
            for (int h = 0; h < 2; h++)
#pragma unroll
                for (int k = 0; k < 4; k++) {
                    const float c = 0.5f * (k == 0 ? a[h].x : k == 1 ? a[h].y : k == 2 ? a[h].z : a[h].w), c1 = c - rbf(c), c2 = c1 - rbf(c1);
                    *reinterpret_cast<uint4*>(stg + A1_SM_XB + (4 * min(tid - 288 + 32 * h, 59) + k) * 16) = make_uint4(pack2(c, c1), pack2(c2, 0.f), 0u, 0u);
                }
            fence_async_smem();
            __syncwarp();
            if (tid == 288) mbar_arrive(bar_stat);
#pragma unroll 4
            for (int k = 0; k < 40; k++) asm volatile("st.global.v4.u32 [%0], {%1,%1,%1,%1};" ::"l"(of + (mb * 8 + hg) * 1280 + 32 * k + (tid - 288)), "r"(~0u) : "memory");
            asm volatile("fence.acq_rel.gpu;" ::: "memory");
            asm volatile("fence.proxy.async.global;" ::: "memory");
            __syncwarp();
            if (tid == 288) mbar_arrive(bar_done);
            if (layer == YT_LAYER) {
#pragma unroll 4
                for (int k = tid - 288; k < 5 * XCP / 8; k += 32) asm volatile("st.global.v4.u32 [%0], {%1,%1,%1,%1};" ::"l"(reinterpret_cast<uint4*>(g_yT) + tile * (5 * XCP / 8) + k), "r"(~0u) : "memory");
            }
            TSTAMP1T(9, 288);
        } else if (w == 8) {
            asm volatile("bar.sync 3, 64;" ::: "memory");
            if (elect()) {
#pragma unroll 1
                for (int kb = A1_P0; kb < 10; kb++) {
                    if (kb < A1_NST) mbar_wait(bars + 8 * A1_PW, 0);
                    else {
                        mbar_wait(bars + 8 * (A1_NST + kb % A1_NST), ((kb / A1_NST) - 1) & 1);
                        if (layer && kb < 9) mbar_wait(bar_rd + 8 * (kb - A1_NST), 0);
                        mbar_expect_tx(bars + 8 * (kb % A1_NST), A1_STAGE);
                    }
                    issue_x(kb, kb < 5 ? kb + te.kb0 : kb - te.kb0); issue_w(kb);
                    if (kb == A1_WOAT) {
                        mbar_expect_tx(bar_wo, 8 * WOB);
                        bulk_load(sbase + A1_SM_W0, wo + hg * 8 * WOB, 2 * WOB, bar_wo);
                    }
                }
                TSTAMP1T(6, 256);
                mbar_wait(bars + 8 * (A1_NST + 3), 1);
                bulk_load(sbase + A1_SM_W3, wo + (hg * 8 + 3) * WOB, 3 * WOB, bar_wo);
            }
            __syncwarp();
        } else {
            const int j = tid - 320;
            const uint32_t tag = ld_epoch();
            if (tid == 352) sm_started(layer);
            if (layer == 0) {
                const uint4* src = reinterpret_cast<const uint4*>(x0 + (size_t)(mb * 128 + hg * 16 + (j >> 2)) * DM);
                uint4 v[20];
#pragma unroll
                for (int k = 0; k < 20; k++) v[k] = __ldg(src + (j & 3) + 4 * k);
                const float p0 = __uint_as_float(__shfl_sync(~0u, v[0].x, j & 28) << 16);
                float s[2] = {0.f, 0.f}, q[2] = {0.f, 0.f};
#pragma unroll
                for (int k = 0; k < 20; k++) {
                    const uint32_t w[4] = {v[k].x, v[k].y, v[k].z, v[k].w};
#pragma unroll
                    for (int i = 0; i < 4; i++) {
                        const float a = __uint_as_float(w[i] << 16) - p0, b = __uint_as_float(w[i] & 0xffff0000u) - p0;
                        s[0] += a; s[1] += b; q[0] = fmaf(a, a, q[0]); q[1] = fmaf(b, b, q[1]);
                    }
                }
                float s0 = s[0] + s[1], q0 = q[0] + q[1];
#pragma unroll
                for (int o = 1; o <= 2; o <<= 1) { s0 += __shfl_xor_sync(~0u, s0, o); q0 += __shfl_xor_sync(~0u, q0, o); }
                if ((j & 3) == 0) {
                    const float d = s0 * (1.0f / DM);
                    const uint32_t ms = pack2(p0 + d, sqrt_apx(rbf(rbf(fmaxf(fmaf(-d, d, q0 * (1.0f / DM)), 0.f)) + 1e-5f)));
                    asm volatile("st.global.cg.u64 [%0], %1;" ::"l"(g_rstat + mb * 128 + (j & 4) * 16 + hg * 8 + (j >> 3)), "l"(tagw(ms, tag)) : "memory");
                    g_piv[mb * 128 + hg * 16 + ((j >> 2) & 8) + (j & 4) + ((j >> 3) & 3)] = __ushort_as_bfloat16((unsigned short)ms);
                }
            }
            float o[4];
            int row;
            if (layer == 0) {
                ulonglong2 v;
#pragma unroll 1
                for (int it = 0; it < SPIN_MAX; it++) {
                    v = ld_tag2(reinterpret_cast<const ulonglong2*>(g_rstat + mb * 128) + j);
                    if (tag_ok(v, tag)) break;
                    __nanosleep(100);
                }
                o[0] = __uint_as_float((uint32_t)v.x << 16); o[1] = rcp_apx(__uint_as_float((uint32_t)v.x & 0xffff0000u));
                o[2] = __uint_as_float((uint32_t)v.y << 16); o[3] = rcp_apx(__uint_as_float((uint32_t)v.y & 0xffff0000u));
                row = 2 * j;
            } else {
                const int ch = j & 7, kg = (j >> 3) & 3;
                const unsigned char* src = stg + (j >> 5) * 8192 + (hg & 3) * 2048;
                float s[8], q[8], p0[8];
#pragma unroll
                for (int i = 0; i < 8; i++) { s[i] = 0.f; q[i] = 0.f; }
#pragma unroll 1
                for (int it = 0; it < 5; it++) {
                    uint4 v[4];
                    mbar_wait(bars + 8 * (it % A1_NST), it / A1_NST);
#pragma unroll
                    for (int k = 0; k < 4; k++) v[k] = *reinterpret_cast<const uint4*>(src + (it % A1_NST) * A1_STAGE + (4 * k + kg) * 128 + ((ch ^ ((4 * k + kg) & 7)) << 4));
                    if (it == 0) {
                        const uint4 pv = *reinterpret_cast<const uint4*>(src + (ch << 4));
                        const uint32_t w[4] = {pv.x, pv.y, pv.z, pv.w};
#pragma unroll
                        for (int i = 0; i < 4; i++) { p0[2 * i] = __uint_as_float(w[i] << 16); p0[2 * i + 1] = __uint_as_float(w[i] & 0xffff0000u); }
                    }
                    asm volatile("" :: "r"(v[0].x), "r"(v[1].x), "r"(v[2].x), "r"(v[3].x), "f"(p0[0]) : "memory");
                    __syncwarp();
                    if ((tid & 31) == 0) mbar_arrive(bar_rd + 8 * it);
#pragma unroll
                    for (int k = 0; k < 4; k++) {
                        const uint32_t w[4] = {v[k].x, v[k].y, v[k].z, v[k].w};
#pragma unroll
                        for (int i = 0; i < 4; i++) {
                            const float a = __uint_as_float(w[i] << 16) - p0[2 * i], b = __uint_as_float(w[i] & 0xffff0000u) - p0[2 * i + 1];
                            s[2 * i] += a; s[2 * i + 1] += b; q[2 * i] = fmaf(a, a, q[2 * i]); q[2 * i + 1] = fmaf(b, b, q[2 * i + 1]);
                        }
                    }
                }
#pragma unroll
                for (int i = 0; i < 4; i++) {
                    const bool up = kg & 2;
                    const float ss = __shfl_xor_sync(~0u, up ? s[i] : s[i + 4], 16), qq = __shfl_xor_sync(~0u, up ? q[i] : q[i + 4], 16);
                    s[i] = (up ? s[i + 4] : s[i]) + ss; q[i] = (up ? q[i + 4] : q[i]) + qq; p0[i] = up ? p0[i + 4] : p0[i];
                }
#pragma unroll
                for (int i = 0; i < 2; i++) {
                    const bool up = kg & 1;
                    const float ss = __shfl_xor_sync(~0u, up ? s[i] : s[i + 2], 8), qq = __shfl_xor_sync(~0u, up ? q[i] : q[i + 2], 8);
                    s[i] = (up ? s[i + 2] : s[i]) + ss; q[i] = (up ? q[i + 2] : q[i]) + qq; p0[i] = up ? p0[i + 2] : p0[i];
                }
                uint4* gp = g_halo + 86016 + mb * 512 + j;
                const float d0 = s[0] * (1.0f / 80.0f), d1 = s[1] * (1.0f / 80.0f);
                asm volatile("st.relaxed.gpu.global.v4.f32 [%0], {%1,%2,%3,%4};" ::"l"(gp + hg * 64), "f"(p0[0] + d0), "f"(fmaxf(fmaf(-d0, s[0], q[0]), 0.f)), "f"(p0[1] + d1), "f"(fmaxf(fmaf(-d1, s[1], q[1]), 0.f)) : "memory");
                __nanosleep(ST_SLEEP0);
                uint32_t pw[8][4], todo = 0xff;
#pragma unroll 1
                for (int it = 0; it < SPIN_MAX; it++) {
#pragma unroll
                    for (int k = 0; k < 8; k++)
                        if (todo >> k & 1) asm volatile("ld.relaxed.gpu.global.v4.u32 {%0,%1,%2,%3}, [%4];" : "=r"(pw[k][0]), "=r"(pw[k][1]), "=r"(pw[k][2]), "=r"(pw[k][3]) : "l"(gp + k * 64) : "memory");
#pragma unroll
                    for (int k = 0; k < 8; k++)
                        if (__all_sync(~0u, pw[k][0] != ~0u && pw[k][1] != ~0u && pw[k][2] != ~0u && pw[k][3] != ~0u)) todo &= ~(1u << k);
                    if (!todo) break;
                    __nanosleep(ST_SLEEP);
                }
#pragma unroll
                for (int r = 0; r < 2; r++) {
                    float mean = 0.f, m2 = 0.f;
#pragma unroll
                    for (int k = 0; k < 8; k++) mean += __uint_as_float(pw[k][2 * r]);
                    mean *= 0.125f;
#pragma unroll
                    for (int k = 0; k < 8; k++) {
                        const float dm = __uint_as_float(pw[k][2 * r]) - mean;
                        m2 += fmaf(80.0f * dm, dm, __uint_as_float(pw[k][2 * r + 1]));
                    }
                    o[2 * r] = rbf(mean);
                    o[2 * r + 1] = rcp_apx(rbf(sqrt_apx(rbf(rbf(m2 * (1.0f / DM)) + 1e-5f))));
                }
                row = (j >> 5) * 64 + (j & 7) * 8 + ((j >> 3) & 3) * 2;
                if (hg == 0) *reinterpret_cast<uint32_t*>(g_piv + SEQ + mb * 128 + 2 * (row & 60) + 4 * (row >> 6) + (row & 3)) = __byte_perm(__float_as_uint(o[0]), __float_as_uint(o[2]), 0x7632);
            }
#pragma unroll
            for (int r = 0; r < 2; r++)
                *reinterpret_cast<uint4*>(stg + A1_SM_XA + (row + r) * 16) = make_uint4(__byte_perm(__float_as_uint(-o[2 * r]), 0, 0x3232), __float_as_uint(-o[2 * r]) >> 16, 0u, 0u);
            *reinterpret_cast<float4*>(rst + row + (row >> 6) * 8) = make_float4(o[0], o[1], o[2], o[3]);
            fence_async_smem();
            TSTAMP1T(7, 320);
            if (tid == 320) DBGC(44);
            __syncwarp();
            if ((tid & 31) == 0) mbar_arrive(bar_stat);
        }
        if (tid == 320) DBGCAL(0);
        if (tid == WOT) {
            mbar_wait(WO_LATE, 0);
            mbar_wait(bar_done, 0);
            bulk_load(sbase, wo + (hg * 8 + 6) * WOB, 2 * WOB, bar_wo);
            bulk_load(sbase + A1_SM_W0 + 2 * WOB, wo + (hg * 8 + 2) * WOB, WOB, bar_wo);
        }
        __syncwarp();
#define FWA 11
#define FWB 10
        if (w == FWA || w == FWB) {
            const int cw = w == FWB;
            const uint32_t* fl = reinterpret_cast<const uint32_t*>(rsum + 2 * SEQ) + (((layer * 16 + mb) * 2 + cw) * 8 + (tid & 7)) * FSTR;
            const unsigned char* src = reinterpret_cast<const unsigned char*>(of) + mb * 163840 + cw * 10240 + (tid & 7) * 20480;
            const uint32_t sl = sbase + (cw ? A1_SM_A1 : A1_SM_A0);
            mbar_wait(cw ? bar_done : bar_kvf, 0);
            if ((tid & 31) == 0) {
                mbar_expect_tx(bar_f2 + 64 * cw + 64, 10240);
                tma_load_3d(sl + 51200, &tmR, layer ? 0 : hg * 80, layer ? hg * 80 : mb * 64, layer ? mb * 2 + cw : cw, bar_f2 + 64 * cw + 64);
            }
            __syncwarp();
            uint32_t pend = 0xffu & ~(1u << hg), v = 0;
            const uint32_t bo = wo_off((tid & 7) + ((tid & 7) < hg)) >> 4, lt = (1u << (tid & 31)) - 1;
#pragma unroll 1
            for (int it = 0; pend && it < 2 * SPIN_MAX; it++) {
                if (v != 4 && (pend >> (tid & 31) & 1)) asm volatile(A1_FLD " %0, [%1];" : "=r"(v) : "l"(fl) : "memory");
                uint32_t fr;
                asm volatile("{\n.reg .pred p;\nmbarrier.test_wait.parity.shared::cta.b64 p, [%1], 0;\nselp.b32 %0, 1, 0, p;\n}" : "=r"(fr) : "r"(bar_e2 + 16 * cw + (tid & 1) * 8) : "memory");
                fr = __ballot_sync(~0u, fr);
                uint32_t m = __ballot_sync(~0u, v == 4 || it >= A1_FSPIN) & pend;
                const int q = 8 - __popc(pend) + __popc(m & lt);
                m &= __ballot_sync(~0u, q < ((fr & 2) ? 8 : (fr & 1) ? 7 : 5));
                pend ^= m;
                if (m >> (tid & 31) & 1) DBGC(12 + cw * 8 + (tid & 7));
                if (!m) __nanosleep(A1_FSLEEP);
                else asm volatile("fence.proxy.async.global;" ::: "memory");
                if (m >> (tid & 31) & 1) {
                    bulk_load(q == 7 && !cw ? sbase + A1_SM_W0 : sl + (q < 6 ? q : q - 6) * 10240, src, 10240, bar_f2 + 64 * cw + 8 * q);
                    asm volatile("st.shared.u32 [%0], %1;" ::"r"(que + 32 * cw + 4 * q), "r"(bo) : "memory");
                    mbar_expect_tx(bar_f2 + 64 * cw + 8 * q, 10240);
                    DBGC(44 + cw * 8 + q);
                }
                __syncwarp();
            }
        }
    } else {
        if (tid == 0) {
            mbar_init(bar_stat, 3);
#pragma unroll
            for (int i = 0; i < 8; i++) mbar_init(bar_kv + 8 * i, 1);
            mbar_init(bars + 144, 1);
            mbar_init(bars + 160, 1);
#pragma unroll
            for (int i = 0; i < 5; i++) mbar_init(bar_rd + 8 * i, 2);
            asm volatile("fence.mbarrier_init.release.cluster;" ::: "memory");
        } else if (tid == 32) {
            mbar_init(bar_wo, 1); mbar_init(bar_done, 3); mbar_init(bar_pv, 4); mbar_init(bar_kvf, 8);
#pragma unroll
            for (int i = 0; i < 4; i++) { mbar_init(bar_e2 + 8 * i, i == 1 ? 2 : 1); mbar_init(bars + 8 * (A1_NST + i), 2); }
            asm volatile("fence.mbarrier_init.release.cluster;" ::: "memory");
        } else if (tid == 96) {
#pragma unroll
            for (int i = 0; i < 4; i++) mbar_init(bars + 416 + 8 * i, 1);
            asm volatile("fence.mbarrier_init.release.cluster;" ::: "memory");
        } else if (tid == 64) {
#pragma unroll
            for (int i = 1; i <= 16; i++) mbar_init(bar_f2 + 8 * i, 1);
            asm volatile("fence.mbarrier_init.release.cluster;" ::: "memory");
        }
        asm volatile("bar.sync 0, 384;" ::: "memory");
        SPAN(1 + 4 * layer, 0);
        constexpr int on = 1;
        float acc[120];
        const int lane = tid & 31, warp = w & 7, g = lane >> 2, t = lane & 3;
        if (on) {
            SPAN(1 + 4 * layer, 1);
            TSTAMP1(0);
            if (threadIdx.x == 0) { GSTAMP(g_tim1, 15); }
            TSTAMP3(0);
            if (tid == 0) TSTAMP2(0);
            TSTAMP4(0);
            if (tid == 0) DBGC(60);
            if (layer == 0) a1_mainloop<0>(acc, sbase, bars, wg, tile); else a1_mainloop<1>(acc, sbase, bars, wg, tile);
            uint32_t ok;
            asm volatile("{\n.reg .pred p;\nmbarrier.test_wait.parity.shared::cta.b64 p, [%1], 0;\nselp.b32 %0, 1, 0, p;\n}" : "=r"(ok) : "r"(bar_stat) : "memory");
            if (tid == 128 && !ok) mbar_arrive(bars + 160);
            __syncwarp();
            mbar_wait(bar_stat, 0);
            wgmma_fence();
            wgmma_n240<0, 0>(acc, make_desc(sbase + A1_SM_XA + wg * 1024, 0, 128, 0), make_desc(sbase + A1_SM_XB, 0, 128, 0), 1);
            wgmma_commit();
            if (tid == 128 && ok) mbar_arrive(bars + 160);
            mbar_wait(bars + 8 * (A1_NST + 3), 1);
        }
        const float2* rw = rst + 16 * warp + 8 * wg;
        const float rb0 = rw[g + 8].y, ra = rw[g].y * 0.22360679774997896f, rb = rb0 * 0.22360679774997896f;
        wgmma_wait<0>();
        if ((tid & 127) == 0) mbar_arrive(bar_done);
        TSTAMP1(2);
        TSTAMP1T(13, 224);
        if ((tid & 127) == 0) DBGC(62 - wg);
        uint32_t f[2][30];
#pragma unroll
        for (int j = 10; j < 30; j++) f[1][j] = pack2(acc[4 * j + 2], acc[4 * j + 3]);
        if ((warp & 3) == 3) {
            uint4* hout = g_halo + (((layer * 16 + mb) * 8 + hg) * 2 + wg) * 168;
#pragma unroll
            for (int j = 0; j < 20; j += 4)
                asm volatile("st.relaxed.gpu.global.v4.u32 [%0], {%1,%2,%3,%4};" ::"l"(hout + 8 * j + lane), "r"(f[1][10 + j]), "r"(f[1][11 + j]), "r"(f[1][12 + j]), "r"(f[1][13 + j]) : "memory");
            if (t == 0) asm volatile("st.relaxed.gpu.global.f32 [%0], %1;" ::"l"(reinterpret_cast<float*>(hout + 160) + g), "f"(rb0) : "memory");
        }
        TSTAMP1T(12, 224);
        const uint32_t kvw = sbase + A1_SM_KV + (16 * warp + 8 * wg) * A1_KVP;
        const uint32_t mrow = kvw + (lane & 7) * A1_KVP + (lane >> 3) * 16;
#pragma unroll
        for (int j = 0; j < 20; j += 4) stsm_x4(mrow + 16 * A1_KVP + 16 * j, f[1][10 + j], f[1][11 + j], f[1][12 + j], f[1][13 + j]);
        __syncwarp();
        if (lane == 0 && (warp & 3) != 3) mbar_arrive(bar_kv + 8 * (warp + 1));
#pragma unroll
        for (int j = 0; j < 30; j++) f[0][j] = pack2(acc[4 * j], acc[4 * j + 1]);
        stsm_x4(mrow + 8 * A1_KVP + 160, f[0][20], f[0][21], f[0][22], f[0][23]);
        stsm_x4(mrow + 8 * A1_KVP + 224, f[0][24], f[0][25], f[0][26], f[0][27]);
        asm volatile("stmatrix.sync.aligned.m8n8.x2.shared.b16 [%0], {%1,%2};" ::"r"(mrow + 8 * A1_KVP + 288), "r"(f[0][28]), "r"(f[0][29]) : "memory");
#pragma unroll
        for (int j = 0; j < 10; j++) f[1][j] = pack2(acc[4 * j + 2], acc[4 * j + 3]);
        __syncwarp();
        uint32_t vb[10][2], vp[12], kp[12];
#pragma unroll
        for (int j = 0; j < 10; j += 2) ldsm_x4_t(&vb[j][0], kvw + (8 + (lane & 15)) * A1_KVP + 160 + (lane >> 4) * 16 + 16 * j);
        const bool up0 = 2 * t > g, up1 = 2 * t + 1 > g, edge = (mb | (warp & 3)) == 0;
        float rk[4];
        auto above = [&]() {
            mbar_wait(bar_kv + 8 * warp, 0);
#pragma unroll
            for (int j = 0; j < 12; j += 4) ldsm_x4(&kp[j], mrow + 16 * j);
            rk[0] = rw[2 * t - (up0 ? 8 : 0)].y; rk[1] = rw[2 * t + 1 - (up1 ? 8 : 0)].y;
#pragma unroll
            for (int j = 0; j < 12; j += 4) ldsm_x4_t(&vp[j], mrow + 160 + 16 * j - (j == 8 ? (lane & 16) * 2 : 0));
            __syncwarp();
            if (lane == 0) mbar_arrive(bar_kvf);
        };
        auto halo = [&]() {
            if (lane == 0) mbar_arrive(bar_kvf);
            const uint4* hin = g_halo + (((layer * 16 + mb - 1) * 8 + hg) * 2 + wg) * 168;
            uint32_t hv[22] = {};
            rk[0] = rw[2 * t].y; rk[1] = rw[2 * t + 1].y;
            if (mb > 0) {
#pragma unroll 1
                for (int it = 0; it < SPIN_MAX; it++) {
#pragma unroll
                    for (int k = 0; k < 20; k += 4)
                        asm volatile("ld.relaxed.gpu.global.v4.u32 {%0,%1,%2,%3}, [%4];" : "=r"(hv[k]), "=r"(hv[k + 1]), "=r"(hv[k + 2]), "=r"(hv[k + 3]) : "l"(hin + 8 * k + lane) : "memory");
                    asm volatile("ld.relaxed.gpu.global.v2.u32 {%0,%1}, [%2];" : "=r"(hv[20]), "=r"(hv[21]) : "l"(reinterpret_cast<const uint2*>(hin + 160) + t) : "memory");
                    uint32_t m = max(hv[20], hv[21]);
#pragma unroll
                    for (int k = 0; k < 20; k += 2) m = __vimax3_u32(m, hv[k], hv[k + 1]);
                    if (!__any_sync(~0u, m == ~0u)) break;
                }
            }
            if (tid == 0) mbar_arrive(bars + 144);
            if (lane == 0) DBGC(52 - 16 * wg);
#pragma unroll
            for (int j = 0; j < 10; j++) {
                kp[j] = hv[j];
                asm volatile("movmatrix.sync.aligned.m8n8.trans.b16 %0, %1;" : "=r"(vp[j]) : "r"(hv[10 + j]));
            }
            if (up0) rk[0] = __uint_as_float(hv[20]);
            if (up1) rk[1] = __uint_as_float(hv[21]);
        };
        rk[2] = rw[2 * t + (up0 ? 0 : 8)].y; rk[3] = rw[2 * t + 1 + (up1 ? 0 : 8)].y;
        uint32_t qs[4][2];
#pragma unroll
        for (int h = 0; h < 4; h++) {
            qs[h][0] = (t >> 1) == (h & 1) ? f[0][5 * (h >> 1) + 2] : 0u; qs[h][1] = (t >> 1) == (h & 1) ? f[1][5 * (h >> 1) + 2] : 0u;
            asm volatile("" : "+r"(qs[h][0]), "+r"(qs[h][1]));
        }
#pragma unroll
        for (int j = 0; j < 10; j++) asm volatile("" : "+r"(f[0][j]), "+r"(f[1][j]), "+r"(f[0][10 + j]));
        if (warp & 3) above(); else if (wg) halo();
        TSTAMP1T(10, 64);
        if (warp && !wg) mbar_wait(bars + 416 + 8 * warp, 0);
        float sc[4][3][4];
#pragma unroll
        for (int h = 0; h < 4; h++) {
            const int jb = 5 * (h >> 1) + 3 * (h & 1), js = 5 * (h >> 1) + 2;
#pragma unroll
            for (int nt = 1; nt < 3; nt++) {
#pragma unroll
                for (int e = 0; e < 4; e++) sc[h][nt][e] = 0.f;
                mma_bf16(sc[h][nt], f[0][jb], f[1][jb], f[0][jb + 1], f[1][jb + 1], f[nt - 1][10 + jb], f[nt - 1][11 + jb]);
                mma_bf16_k8(sc[h][nt], qs[h][0], qs[h][1], f[nt - 1][10 + js]);
            }
        }
        if (warp == 0) halo();
        TSTAMP1(8);
#pragma unroll
        for (int h = 0; h < 4; h++) {
            const int jb = 5 * (h >> 1) + 3 * (h & 1), js = 5 * (h >> 1) + 2;
#pragma unroll
            for (int e = 0; e < 4; e++) sc[h][0][e] = 0.f;
            mma_bf16(sc[h][0], f[0][jb], f[1][jb], f[0][jb + 1], f[1][jb + 1], kp[jb], kp[jb + 1]);
            mma_bf16_k8(sc[h][0], qs[h][0], qs[h][1], kp[js]);
        }
        TSTAMP1T(3, 64);
        float p[4][4], sum[4][2];
        uint32_t lg[4][2], mx[4];
        const float rl[4] = {rk[0] * ra, rk[1] * ra, rk[2] * rb, rk[3] * rb};
        auto max2 = [](uint32_t a, uint32_t b) { uint32_t r; asm("max.bf16x2 %0, %1, %2;" : "=r"(r) : "r"(a), "r"(b)); return r; };
#pragma unroll
        for (int h = 0; h < 4; h++) {
            lg[h][0] = pack2((up0 ? sc[h][0][0] : sc[h][1][0]) * rl[0], (up0 ? sc[h][1][2] : sc[h][2][2]) * rl[2]);
            lg[h][1] = pack2((up1 ? sc[h][0][1] : sc[h][1][1]) * rl[1], (up1 ? sc[h][1][3] : sc[h][2][3]) * rl[3]);
            if (edge) {
                if (up0) lg[h][0] = __byte_perm(lg[h][0], 0xce6eu, 0x3254);
                if (up1) lg[h][1] = __byte_perm(lg[h][1], 0xce6eu, 0x3254);
            }
            mx[h] = max2(lg[h][0], lg[h][1]);
        }
#pragma unroll
        for (int o = 1; o <= 2; o <<= 1)
#pragma unroll
            for (int h = 0; h < 4; h++) mx[h] = max2(mx[h], __shfl_xor_sync(~0u, mx[h], o));
#pragma unroll
        for (int h = 0; h < 4; h++)
#pragma unroll
            for (int r = 0; r < 2; r++) {
                const float m = __uint_as_float(r ? mx[h] & 0xffff0000u : mx[h] << 16);
#pragma unroll
                for (int e = 0; e < 2; e++)
                    asm("ex2.approx.ftz.f32 %0, %1;" : "=f"(p[h][2 * r + e]) : "f"((__uint_as_float(r ? lg[h][e] & 0xffff0000u : lg[h][e] << 16) - m) * 1.4426950408889634f));
                sum[h][r] = p[h][2 * r] + p[h][2 * r + 1];
            }
#pragma unroll
        for (int o = 1; o <= 2; o <<= 1)
#pragma unroll
            for (int h = 0; h < 4; h++)
#pragma unroll
                for (int r = 0; r < 2; r++) sum[h][r] += __shfl_xor_sync(~0u, sum[h][r], o);
        TSTAMP1T(5, 64);
        const uint32_t mu = (up0 ? 0xffffu : 0u) | (up1 ? 0xffff0000u : 0u);
        uint32_t ob[10][2];
#pragma unroll
        for (int P = 0; P < 2; P++) {
            float os[2][4];
#pragma unroll
            for (int e = 0; e < 2; e++) {
                const int h = 2 * P + e;
                const float i0 = rcp_apx(sum[h][0]), i1 = rcp_apx(sum[h][1]);
                const uint32_t w0 = pack2(p[h][0] * rk[0] * i0, p[h][1] * rk[1] * i0), w1 = pack2(p[h][2] * rk[2] * i1, p[h][3] * rk[3] * i1);
#pragma unroll
                for (int dt = 0; dt < 3; dt++) {
                    const int j = 5 * P + (dt < 2 ? 3 * e + dt : 2);
                    float o[4] = {0.f, 0.f, 0.f, 0.f};
                    mma_bf16(o, w0 & ~mu, w1 & mu, 0u, w1 & ~mu, vb[j][0], vb[j][1]);
                    mma_bf16_k8(o, w0 & mu, 0u, vp[j]);
                    if (dt < 2) { ob[j][0] = pack2(o[0], o[1]); ob[j][1] = pack2(o[2], o[3]); }
                    else { os[e][0] = o[0]; os[e][1] = o[1]; os[e][2] = o[2]; os[e][3] = o[3]; }
                }
            }
#pragma unroll
            for (int k = 0; k < 4; k++) os[0][k] = t < 2 ? os[0][k] : os[1][k];
            ob[5 * P + 2][0] = pack2(os[0][0], os[0][1]); ob[5 * P + 2][1] = pack2(os[0][2], os[0][3]);
        }
        const uint32_t sl = sbase + (wg ? A1_SM_A1 : A1_SM_A0);
        const uint32_t o0 = (warp & 3) * 2048 + g * 64 + ((t ^ (g >> 1)) << 4), o1 = 8192 + (warp & 3) * 512 + g * 32 + ((t ^ ((g >> 2) << 1)) << 3);
        mbar_wait(bar_done, 0);
        if (wg == 0) mbar_wait(bar_kvf, 0);
#pragma unroll
        for (int h = 0; h < 2; h++) {
            asm volatile("st.shared.v4.u32 [%0], {%1,%2,%3,%4};" ::"r"(sl + o0 + h * 1024), "r"(ob[0][h]), "r"(ob[1][h]), "r"(ob[2][h]), "r"(ob[3][h]) : "memory");
            asm volatile("st.shared.v4.u32 [%0], {%1,%2,%3,%4};" ::"r"(sl + o0 + h * 1024 + 512), "r"(ob[4][h]), "r"(ob[5][h]), "r"(ob[6][h]), "r"(ob[7][h]) : "memory");
            asm volatile("st.shared.v2.u32 [%0], {%1,%2};" ::"r"(sl + o1 + h * 256), "r"(ob[8][h]), "r"(ob[9][h]) : "memory");
        }
        if (wg && lane == 0) mbar_arrive(bars + 384 + 8 * warp);
        fence_async_smem();
        __syncwarp();
        TSTAMP1T(4, 64);
        TSTAMP1(1);
        TSTAMP2(1);
        const unsigned char* ot = reinterpret_cast<const unsigned char*>(of) + mb * 163840 + wg * 10240;
        if (lane == 0) {
            asm volatile("cp.async.bulk.global.shared::cta.bulk_group [%0], [%1], 2048;" ::"l"(ot + hg * 20480 + (warp & 3) * 2048), "r"(sl + (warp & 3) * 2048) : "memory");
            asm volatile("cp.async.bulk.global.shared::cta.bulk_group [%0], [%1], 512;" ::"l"(ot + hg * 20480 + 8192 + (warp & 3) * 512), "r"(sl + 8192 + (warp & 3) * 512) : "memory");
            asm volatile("cp.async.bulk.commit_group;" ::: "memory");
            if (wg == 0) mbar_arrive(bar_pv);
            asm volatile("cp.async.bulk.wait_group 0;" ::: "memory");
            asm volatile(A1_FRED " [%0], 1;" ::"l"(reinterpret_cast<uint32_t*>(rsum + 2 * SEQ) + (((layer * 16 + mb) * 2 + wg) * 8 + hg) * FSTR) : "memory");
            DBGC(4 + warp);
        }
        TSTAMP4(11);
        float ac2[40];
        const uint64_t db0 = make_desc(sbase, 1024, 256, 3), db1 = make_desc(sbase + 10240, 512, 256, 3), da0 = make_desc(sl, 16, 1024, 2), da1 = make_desc(sl + 8192, 16, 256, 3);
        const uint32_t o7 = wg ? 640 : (A1_SM_W0 - A1_SM_A0) >> 4;
        const uint32_t trow = ((lane & 7) + 8 * (lane >> 4)) * 128 + (((2 * (warp & 3) + ((lane >> 3) & 1)) ^ (lane & 7)) << 4);
        uint32_t xr[10][2];
        mbar_wait(bar_f2 + 64 * wg + 64, 0);
        if (layer == 0) {
#pragma unroll
            for (int j = 0; j < 10; j += 2) ldsm_x4(&xr[j][0], sl + 51200 + (16 * (warp & 3) + (lane & 15)) * 160 + (lane >> 4) * 16 + 16 * j);
        } else {
#pragma unroll
            for (int j = 0; j < 10; j += 2) ldsm_x4_t(&xr[j][0], sl + 51200 + trow + 1024 * j);
        }
        const uint32_t ri = __shfl_sync(~0u, layer * SEQ + (wg * 2 + ((g >> 1) & 1)) * 512 + (mb * 16 + 4 * (warp & 3) + (g >> 2)) * 2 + (g & 1), lane);
        mbar_wait(bar_wo, 0);
        if (wg) mbar_wait(bar_pv, 0);
        if (wg) asm volatile("bar.sync 2, 128;" ::: "memory"); else asm volatile("bar.sync 1, 128;" ::: "memory");
        TSTAMP2(2);
#pragma unroll
        for (int q = 0; q < 8; q++) {
            uint32_t bo = wo_off(0) >> 4;
            if (q) {
                mbar_wait(bar_f2 + 64 * wg + 8 * q, 0);
                asm volatile("ld.shared.u32 %0, [%1];" : "=r"(bo) : "r"(que + 32 * wg + 4 * q) : "memory");
                bo = __shfl_sync(~0u, bo, 0);
                TSTAMP4(q);
                if (q == 1 && (tid & 127) == 0) DBGC(29 + 8 * wg);
            }
            wgmma_fence();
#pragma unroll
            for (int j = 0; j < 5; j++) wgmma_n80(ac2, (j < 4 ? da0 : da1) + (q == 7 ? o7 : 0u) + (uint64_t)((q < 6 ? q * 640 : 0) + (j & 2) * 16 + (j & 1) * 2), (j < 4 ? db0 : db1) + bo + (uint64_t)((j & 2) * 160 + (j & 1) * 32), j || q);
            wgmma_commit();
            if (q == 0) {
                wgmma_wait<0>();
                if ((tid & 127) == 0) { mbar_arrive(bar_e2 + 16 * wg); mbar_arrive(bar_e2 + 8); }
            }
            if (q == 2 && wg) {
                wgmma_wait<1>();
                if (tid == 128) mbar_arrive(bar_e2 + 24);
            }
        }
        if ((tid & 127) == 0) DBGC(28 + wg * 8 + 7);
        TSTAMP2(3);
        wgmma_wait<0>();
        TSTAMP2(4);
        if (__any_sync(~0u, ac2[0] != ac2[0] || ac2[2] != ac2[2])) {
#pragma unroll
            for (int i = 0; i < 40; i++) ac2[i] = 0.f;
            uint32_t a[20], an[20];
            auto lda = [&](uint32_t (&r)[20], int h) {
#pragma unroll
                for (int u = 0; u < 4; u++)
                    asm volatile("ld.relaxed.gpu.global.v4.u32 {%0,%1,%2,%3}, [%4];" : "=r"(r[4 * u]), "=r"(r[4 * u + 1]), "=r"(r[4 * u + 2]), "=r"(r[4 * u + 3]) : "l"(ot + h * 20480 + o0 + u * 512) : "memory");
#pragma unroll
                for (int u = 0; u < 2; u++)
                    asm volatile("ld.relaxed.gpu.global.v2.u32 {%0,%1}, [%2];" : "=r"(r[16 + 2 * u]), "=r"(r[17 + 2 * u]) : "l"(ot + h * 20480 + o1 + u * 256) : "memory");
            };
            lda(an, 0);
#pragma unroll 5
            for (int k = lane; k < WOB / 16; k += 32)
                reinterpret_cast<uint4*>(stg + (sl - sbase))[k] = __ldcg(reinterpret_cast<const uint4*>(wo + hg * 8 * WOB) + k);
            __syncwarp();
#pragma unroll 1
            for (int h = 0; h < 8; h++) {
#pragma unroll 1
                for (int it = 0; it < SPIN_MAX; it++) {
                    uint32_t m = 0;
#pragma unroll
                    for (int k = 0; k < 20; k += 2) m = __vimax3_u32(m, an[k], an[k + 1]);
                    if (!__any_sync(~0u, m == ~0u)) break;
                    lda(an, h);
                }
#pragma unroll
                for (int k = 0; k < 20; k++) a[k] = an[k];
                lda(an, min(h + 1, 7));
                const uint32_t bp = h == hg ? sl : sbase + wo_off(h + (h < hg));
                const int r0 = 8 * ((lane & 7) >> 1) + 2 * (lane >> 3) + (lane & 1), r2 = 4 * ((lane & 7) >> 1) + 2 * ((lane >> 3) & 1) + (lane & 1);
#pragma unroll
                for (int n = 0; n < 10; n++) {
                    uint32_t b[12];
                    ldsm_x4_t(b, bp + (n >> 1) * 1024 + r0 * 32 + (((n ^ (r0 >> 2)) & 1) << 4));
                    ldsm_x4_t(b + 4, bp + 5120 + (n >> 1) * 1024 + r0 * 32 + (((n ^ (r0 >> 2)) & 1) << 4));
                    ldsm_x4_t(b + 8, bp + 10240 + (n >> 1) * 512 + r2 * 32 + (((n ^ (r2 >> 2)) & 1) << 4));
                    mma_bf16(ac2 + 4 * n, a[0], a[8], a[1], a[9], b[0], b[1]); mma_bf16(ac2 + 4 * n, a[2], a[10], a[3], a[11], b[2], b[3]);
                    mma_bf16(ac2 + 4 * n, a[4], a[12], a[5], a[13], b[4], b[5]); mma_bf16(ac2 + 4 * n, a[6], a[14], a[7], a[15], b[6], b[7]);
                    mma_bf16(ac2 + 4 * n, a[16], a[18], a[17], a[19], b[8], b[9]);
                }
            }
        }
#pragma unroll
        for (int j = 0; j < 10; j++)
#pragma unroll
            for (int hh = 0; hh < 2; hh++) {
                const uint32_t a = pack2(ac2[4 * j + 2 * hh], ac2[4 * j + 2 * hh + 1]);
                const __nv_bfloat162 r = __hadd2_rn(*reinterpret_cast<const __nv_bfloat162*>(&xr[j][hh]), *reinterpret_cast<const __nv_bfloat162*>(&a));
                xr[j][hh] = *reinterpret_cast<const uint32_t*>(&r);
            }
        const uint32_t so = sl + 30720;
#pragma unroll
        for (int j = 0; j < 10; j += 2) stsm_x4_t(so + trow + 1024 * j, xr[j][0], xr[j][1], xr[j + 1][0], xr[j + 1][1]);
        fence_async_smem();
        if (wg) asm volatile("bar.sync 2, 128;" ::: "memory"); else asm volatile("bar.sync 1, 128;" ::: "memory");
        TSTAMP2(5);
        if ((tid & 127) == 0) {
            asm volatile("cp.async.bulk.tensor.2d.global.shared::cta.bulk_group [%0, {%1, %2}], [%3];" ::"l"(&tmX1), "r"(mb * 128 + 64 * wg), "r"(hg * 80), "r"(so) : "memory");
            asm volatile("cp.async.bulk.commit_group;" ::: "memory");
        }
        __syncwarp();
        const float p0 = *(volatile const float*)&rw[g].x, p1 = *(volatile const float*)&rw[g + 8].x;
        float s[3][4] = {};
        const uint32_t pp[2] = {__byte_perm(__float_as_uint(p0), 0, 0x3232), __byte_perm(__float_as_uint(p1), 0, 0x3232)};
#pragma unroll
        for (int j = 0; j < 10; j += 2) {
            const uint32_t d0 = sub2(xr[j][0], pp[0]), d1 = sub2(xr[j][1], pp[1]), d2 = sub2(xr[j + 1][0], pp[0]), d3 = sub2(xr[j + 1][1], pp[1]);
            mma_bf16(s[0], xr[j][0], xr[j][1], xr[j + 1][0], xr[j + 1][1], 0x3f803f80u, 0x3f803f80u);
            mma_bf16(s[1], d0, d1, d2, d3, d0, d2);
            mma_bf16(s[2], d0, d1, d2, d3, d1, d3);
        }
        if (t == (g >> 1)) {
            float2* rp = rsum + ri;
            asm volatile("red.relaxed.gpu.global.add.v2.f32 [%0], {%1, %2};" ::"l"(rp), "f"(fmaf(-80.f, p0, s[0][0])), "f"((g & 1) ? s[1][1] : s[1][0]) : "memory");
            asm volatile("red.relaxed.gpu.global.add.v2.f32 [%0], {%1, %2};" ::"l"(rp + 4), "f"(fmaf(-80.f, p1, s[0][2])), "f"((g & 1) ? s[2][3] : s[2][2]) : "memory");
        }
        asm volatile("cp.async.bulk.wait_group.read 0;" ::: "memory");
        TSTAMP2(6);
        if (tid == 0) DBGC(63);
        if (tid == 128) DBGC(28);
        if (tid == 0) DBGCAL(2);
        GSTAMP(g_tim1, 14);
        SPAN(1 + 4 * layer, 3);
    }
}

static int h_nsm;
static void* h_sym[11];
static TileTab h_tab;
static CUtensorMap h_tmX0, h_tmX1, h_tmR0, h_tmR1, h_tmX1st, h_tmOut, h_tmWq, h_tmWo, h_tmWt;
typedef CUresult (*PFN_encodeTiled)(CUtensorMap*, CUtensorMapDataType, cuuint32_t, void*, const cuuint64_t*, const cuuint64_t*,
                                    const cuuint32_t*, const cuuint32_t*, CUtensorMapInterleave, CUtensorMapSwizzle,
                                    CUtensorMapL2promotion, CUtensorMapFloatOOBfill);
static void make_tmap(CUtensorMap* tm, const void* ptr, uint64_t cols, uint64_t rows, uint32_t bc, uint32_t br, CUtensorMapSwizzle sw, uint64_t pitch = 0, uint64_t hi = 0, uint32_t bh = 2) {
    static PFN_encodeTiled fn = nullptr;
    if (!fn) {
        void* p = nullptr; cudaDriverEntryPointQueryResult qr;
        cudaGetDriverEntryPoint("cuTensorMapEncodeTiled", &p, cudaEnableDefault, &qr);
        fn = (PFN_encodeTiled)p;
    }
    if (br == 0) {
        cuuint64_t dims[5] = {16, 2, rows / 8, 4, cols / 16}; cuuint64_t strides[4] = {cols * 2, cols * 16, cols * 4, 32};
        cuuint32_t box[5] = {16, 2, bc, 4, 5}; cuuint32_t es[5] = {1, 1, 1, 1, 1};
        fn(tm, CU_TENSOR_MAP_DATA_TYPE_BFLOAT16, 5, const_cast<void*>(ptr), dims, strides, box, es, CU_TENSOR_MAP_INTERLEAVE_NONE, sw,
           CU_TENSOR_MAP_L2_PROMOTION_L2_128B, CU_TENSOR_MAP_FLOAT_OOB_FILL_NONE);
        return;
    }
    if (bh == 0) {
        cuuint64_t dims[5] = {64, 64, 2, 16, 10}; cuuint64_t strides[4] = {pitch * 2, hi * 2, cols * 2, rows * 2};
        cuuint32_t box[5] = {64, 64, 2, 1, 1}; cuuint32_t es[5] = {1, 1, 1, 1, 1};
        fn(tm, CU_TENSOR_MAP_DATA_TYPE_BFLOAT16, 5, const_cast<void*>(ptr), dims, strides, box, es, CU_TENSOR_MAP_INTERLEAVE_NONE, sw,
           CU_TENSOR_MAP_L2_PROMOTION_L2_128B, CU_TENSOR_MAP_FLOAT_OOB_FILL_NONE);
        return;
    }
    if (hi) {
        cuuint64_t dims[3] = {cols, rows, hi == 64 ? 32u : hi == 16 ? 120u : 2u}; cuuint64_t strides[2] = {pitch * 2, hi * 2};
        cuuint32_t box[3] = {bc, br, bh}; cuuint32_t es[3] = {1, 1, 1};
        fn(tm, CU_TENSOR_MAP_DATA_TYPE_BFLOAT16, 3, const_cast<void*>(ptr), dims, strides, box, es, CU_TENSOR_MAP_INTERLEAVE_NONE, sw,
           CU_TENSOR_MAP_L2_PROMOTION_L2_128B, CU_TENSOR_MAP_FLOAT_OOB_FILL_NONE);
        return;
    }
    cuuint64_t dims[2] = {cols, rows}; cuuint64_t strides[1] = {(pitch ? pitch : cols) * 2};
    cuuint32_t box[2] = {bc, br}; cuuint32_t es[2] = {1, 1};
    fn(tm, CU_TENSOR_MAP_DATA_TYPE_BFLOAT16, 2, const_cast<void*>(ptr), dims, strides, box, es, CU_TENSOR_MAP_INTERLEAVE_NONE, sw,
       CU_TENSOR_MAP_L2_PROMOTION_L2_128B, CU_TENSOR_MAP_FLOAT_OOB_FILL_NONE);
}
template <typename... Args>
static void launch_pdl(void (*kern)(Args...), int grid, int block, int smem, Args... args) {
    cudaLaunchConfig_t cfg = {};
    cfg.gridDim = dim3(grid); cfg.blockDim = dim3(block); cfg.dynamicSmemBytes = smem; cfg.stream = cudaStreamPerThread;
    cudaLaunchAttribute at[1];
    at[0].id = cudaLaunchAttributeProgrammaticStreamSerialization; at[0].val.programmaticStreamSerializationAllowed = 1;
    cfg.attrs = at; cfg.numAttrs = 1;
    cudaLaunchKernelEx(&cfg, kern, args...);
}
static void launch_stage(int k, void* const* d_in, void* d_out) {
    const KgIn kg = {(const bf16*)d_in[4], (const bf16*)d_in[5], (const bf16*)d_in[6], (const bf16*)d_in[7], (const bf16*)d_in[8], (const bf16*)d_in[9], (const bf16*)d_in[0], (const bf16*)d_in[1], (const bf16*)d_in[2],
                      (uint4*)h_sym[0], (uint4*)h_sym[1], (uint4*)h_sym[2], (uint4*)h_sym[3], (uint4*)h_sym[4], (float*)h_sym[5]};
    switch (k) {
        case 0: kgen_kernel<<<128, 512, KG_SMEM, cudaStreamPerThread>>>(kg, h_tmWq, h_tmWo, h_tmWt); break;
        case 1: launch_pdl(a1_kernel, h_nsm, A1_THREADS, A1_SMEM, 0, (const bf16*)d_in[0], (const unsigned char*)h_sym[1], (const unsigned char*)h_sym[2], (float2*)h_sym[4], (uint4*)h_sym[6], h_tmX0, h_tmR0, h_tmX1st, h_tab); break;
        case 3: launch_pdl(conv_kernel, DM / CV_CPB, CV_THREADS, CV_SMEM, 0, (const uint4*)h_sym[7], (const float4*)h_sym[4], (const bf16*)h_sym[8], (bf16*)h_sym[9], (const uint4*)h_sym[0], h_tmOut); break;
        case 5: launch_pdl(a1_kernel, h_nsm, A1_THREADS, A1_SMEM, 1, (const bf16*)d_in[0], (const unsigned char*)h_sym[1], (const unsigned char*)h_sym[2], (float2*)h_sym[4], (uint4*)h_sym[6], h_tmX1, h_tmR1, h_tmX1st, h_tab); break;
        case 7: launch_pdl(conv_kernel, DM / CV_CPB, CV_THREADS, CV_SMEM, 1, (const uint4*)h_sym[7] + SEQ / 8, (const float4*)h_sym[4] + SEQ / 2, (const bf16*)h_sym[8], (bf16*)h_sym[10], (const uint4*)h_sym[0], h_tmOut); break;
        default: break;
    }
}
static int n_stage_kernels() { return 9; }
static const char* stage_name(int k) { const char* n[] = {"kgen", "a1", "a2", "conv", "tr", "a1", "a2", "conv", "tr"}; return n[k]; }

extern "C" void kernel_launch(void* const* d_in, const int* in_sizes, int n_in, void* d_out, int out_size) {
    (void)in_sizes; (void)n_in; (void)out_size;
    static const void *p_in = nullptr, *p_w1 = nullptr, *p_w2 = nullptr, *p_out = nullptr;
    if (p_in != d_in[0] || p_w1 != d_in[1] || p_w2 != d_in[2] || p_out != d_out) {
        cudaFuncSetAttribute(conv_kernel, cudaFuncAttributeMaxDynamicSharedMemorySize, CV_SMEM);
        cudaFuncSetAttribute(kgen_kernel, cudaFuncAttributeMaxDynamicSharedMemorySize, KG_SMEM);
        cudaFuncSetAttribute(a1_kernel, cudaFuncAttributeMaxDynamicSharedMemorySize, A1_SMEM);
        int dev; cudaGetDevice(&dev); cudaDeviceGetAttribute(&h_nsm, cudaDevAttrMultiProcessorCount, dev);
        if (h_nsm != 132) h_nsm = 128;
        h_tab.ns = h_nsm == 132 ? 132 : ~0u;
        for (int i = 0; i < 264; i++) {
            const int h = (i - 64) >> 1;
            const int t = i >= 132 ? i - 132 : i < 64 ? ((i >> 1) & 7) * 16 + (i >> 4) * 2 + (i & 1) : i < 120 ? (1 + h % 7) * 16 + 8 + (h / 7) * 2 + (i & 1) : i < 124 ? 128 : i - 116;
            const int hg = (4 * (t >> 6) + (t & 3)) & 7;
            h_tab.e[i] = {(unsigned char)((t >> 2) & 15), (unsigned char)hg, (unsigned char)(5 * (hg >> 2)), (unsigned char)t, (uint32_t)(hg * 10 * WQ_STAGE)};
        }
        cudaGetSymbolAddress(&h_sym[0], g_tap); cudaGetSymbolAddress(&h_sym[1], g_wq); cudaGetSymbolAddress(&h_sym[2], g_wo);
        cudaGetSymbolAddress(&h_sym[3], g_halo); cudaGetSymbolAddress(&h_sym[4], g_sum); cudaGetSymbolAddress(&h_sym[5], g_csp); cudaGetSymbolAddress(&h_sym[6], g_of);
        cudaGetSymbolAddress(&h_sym[7], g_piv); cudaGetSymbolAddress(&h_sym[8], g_x1T); cudaGetSymbolAddress(&h_sym[9], g_xcT); cudaGetSymbolAddress(&h_sym[10], g_yT);
        void *px1, *px2;
        cudaGetSymbolAddress(&px1, g_x1T); cudaGetSymbolAddress(&px2, g_xcT);
        make_tmap(&h_tmX0, d_in[0], 128 * 640, 64, 64, 64, CU_TENSOR_MAP_SWIZZLE_128B, 1280, 640, 0);
        make_tmap(&h_tmX1, px2, 128, 64 * XCP, 64, 64, CU_TENSOR_MAP_SWIZZLE_128B, XCP, 64, 0);
        make_tmap(&h_tmR0, d_in[0], 640, 1024, 80, 64, CU_TENSOR_MAP_SWIZZLE_NONE, 1280, 640, 1);
        make_tmap(&h_tmR1, px2, 64, 640, 64, 80, CU_TENSOR_MAP_SWIZZLE_128B, XCP, 64, 1);
        make_tmap(&h_tmX1st, px1, 2048, 640, 64, 80, CU_TENSOR_MAP_SWIZZLE_128B, XCP);
        make_tmap(&h_tmWq, d_in[1], 16, 640, 16, 32, CU_TENSOR_MAP_SWIZZLE_32B, 1920, 16, 5);
        make_tmap(&h_tmWo, d_in[2], 640, 640, 4, 0, CU_TENSOR_MAP_SWIZZLE_32B);
        make_tmap(&h_tmWt, d_in[2], 640, 640, 2, 0, CU_TENSOR_MAP_SWIZZLE_32B);
        make_tmap(&h_tmOut, d_out, 640, 1024, 80, 8, CU_TENSOR_MAP_SWIZZLE_NONE, 1280, 640, 1);
        p_in = d_in[0]; p_w1 = d_in[1]; p_w2 = d_in[2]; p_out = d_out;
    }
    for (int k = 0; k < n_stage_kernels(); k++) launch_stage(k, d_in, d_out);
}
```

```cpp
#include <cuda_runtime.h>
#include <cuda_bf16.h>
#include <stdint.h>
#include <cuda.h>

typedef __nv_bfloat16 bf16;

constexpr int SEQ = 2048;
constexpr int DM = 640;
constexpr int NMODE = 192;

__device__ __forceinline__ float bf2f(bf16 v) { return __bfloat162float(v); }
__device__ __forceinline__ float rbf(float v) {
    uint32_t r;
    asm("cvt.rn.bf16x2.f32 %0, %1, %2;" : "=r"(r) : "f"(v), "f"(0.f));
    return __uint_as_float(r);
}
__device__ __forceinline__ uint32_t pack2(float lo, float hi) {
    __nv_bfloat162 t = __floats2bfloat162_rn(lo, hi);
    return *reinterpret_cast<uint32_t*>(&t);
}
__device__ __forceinline__ void pdl_sync() {
    asm volatile("griddepcontrol.wait;" ::: "memory");
    asm volatile("griddepcontrol.launch_dependents;" ::: "memory");
}
__device__ __forceinline__ float sqrt_apx(float v) { float r; asm("sqrt.approx.ftz.f32 %0, %1;" : "=f"(r) : "f"(v)); return r; }
__device__ __forceinline__ float rcp_apx(float v) { float r; asm("rcp.approx.ftz.f32 %0, %1;" : "=f"(r) : "f"(v)); return r; }
__device__ __forceinline__ uint32_t smem_u32(const void* p) { return (uint32_t)__cvta_generic_to_shared(p); }

constexpr int TAPB = 2 * 152 * 8;
__device__ __align__(128) uint4 g_tap[DM * 128];
#define XPAD 64
constexpr int XCP = SEQ + XPAD;
__device__ __align__(128) bf16 g_x1T[DM * XCP];
__device__ __align__(128) bf16 g_xcT[DM * XCP];
__device__ __align__(128) uint4 g_of[128 * 1280];
constexpr int WQ_STAGE = 240 * 128, WOB = 80 * 160;
__device__ __align__(128) uint4 g_wq[8 * 10 * WQ_STAGE / 16];
__device__ __align__(128) uint4 g_wo[64 * WOB / 16];
__device__ __align__(16) float g_csp[10 * 1920];
#define FSTR 32
__device__ __align__(128) float2 g_sum[2 * SEQ + 256 * FSTR];
__device__ __align__(16) bf16 g_piv[2 * SEQ];
__device__ __align__(128) bf16 g_yT[DM * XCP];
__device__ uint32_t g_epoch;
__device__ __align__(16) unsigned long long g_rstat[SEQ];
__device__ __align__(128) uint4 g_halo[640 * 148];
__device__ __forceinline__ unsigned long long tagw(uint32_t payload, uint32_t tag) { return ((unsigned long long)tag << 32) | payload; }
__device__ __forceinline__ ulonglong2 ld_tag2(const ulonglong2* p) {
    ulonglong2 v;
    asm volatile("ld.relaxed.gpu.global.v2.u64 {%0, %1}, [%2];" : "=l"(v.x), "=l"(v.y) : "l"(p) : "memory");
    return v;
}
__device__ __forceinline__ bool tag_ok(ulonglong2 v, uint32_t tag) { return (uint32_t)(v.x >> 32) == tag && (uint32_t)(v.y >> 32) == tag; }
__device__ __forceinline__ uint32_t ld_epoch() { uint32_t v; asm volatile("ld.relaxed.gpu.global.u32 %0, [%1];" : "=r"(v) : "l"(&g_epoch) : "memory"); return v + 1; }
constexpr int SPIN_MAX = 1 << 20;
__device__ uint32_t g_started[4];
__device__ __forceinline__ void sm_started(int slot) { asm volatile("red.relaxed.gpu.global.add.u32 [%0], 1;" ::"l"(g_started + slot) : "memory"); }
__device__ __noinline__ void sm_idle(int slot) {
    if (threadIdx.x) return;
    sm_started(slot);
    const uint32_t want = ld_epoch() * gridDim.x;
    pdl_sync();
#pragma unroll 1
    for (int it = 0; it < SPIN_MAX; it++) {
        uint32_t v;
        asm volatile("ld.relaxed.gpu.global.u32 %0, [%1];" : "=r"(v) : "l"(g_started + slot) : "memory");
        if ((int)(v - want) >= 0) break;
        __nanosleep(100);
    }
}
struct TileTab { uint32_t ns, pad; struct { unsigned char mb, hg, kb0, tile; uint32_t woff; } __align__(8) e[264]; };
__device__ __forceinline__ bool elect() {
    uint32_t p;
    asm volatile("{\n.reg .pred p;\nelect.sync _|p, 0xffffffff;\nselp.b32 %0, 1, 0, p;\n}" : "=r"(p));
    return p;
}
#define DBG_SYMS
#define TSTAMP(i)
#define TSTAMP1(i)
#define TSTAMP1T(i, t)
#define TSTAMP1X(i, t)
#define SPAN(k, i)
#define GSTAMP(arr, i)
#define TSTAMP2(i)
#define TSTAMP3(i)
#define TSTAMP4(i)
#define TSTAMPK(i, t)
#define TSTAMPC(i)
#define DBGC(i)
#define DBGV(i, v)
#define DBGCAL(i)

#define CST(i)
#define CST_END
#define CST_EXTRA 0
__device__ __forceinline__ void mma_bf16(float* d, uint32_t a0, uint32_t a1, uint32_t a2, uint32_t a3, uint32_t b0, uint32_t b1) {
    asm volatile("mma.sync.aligned.m16n8k16.row.col.f32.bf16.bf16.f32 {%0,%1,%2,%3}, {%4,%5,%6,%7}, {%8,%9}, {%0,%1,%2,%3};"
                 : "+f"(d[0]), "+f"(d[1]), "+f"(d[2]), "+f"(d[3]) : "r"(a0), "r"(a1), "r"(a2), "r"(a3), "r"(b0), "r"(b1));
}
__device__ __forceinline__ void mma_bf16_k8(float* d, uint32_t a0, uint32_t a1, uint32_t b0) {
    asm volatile("mma.sync.aligned.m16n8k8.row.col.f32.bf16.bf16.f32 {%0,%1,%2,%3}, {%4,%5}, {%6}, {%0,%1,%2,%3};"
                 : "+f"(d[0]), "+f"(d[1]), "+f"(d[2]), "+f"(d[3]) : "r"(a0), "r"(a1), "r"(b0));
}
__device__ __forceinline__ void ldsm_x4(uint32_t* r, uint32_t addr) {
    asm volatile("ldmatrix.sync.aligned.m8n8.x4.shared.b16 {%0,%1,%2,%3}, [%4];"
                 : "=r"(r[0]), "=r"(r[1]), "=r"(r[2]), "=r"(r[3]) : "r"(addr));
}

__device__ __forceinline__ void ldsm_x4_t(uint32_t* r, uint32_t addr) {
    asm volatile("ldmatrix.sync.aligned.m8n8.x4.trans.shared.b16 {%0,%1,%2,%3}, [%4];"
                 : "=r"(r[0]), "=r"(r[1]), "=r"(r[2]), "=r"(r[3]) : "r"(addr));
}
__device__ __forceinline__ void mbar_init(uint32_t bar, int count) { asm volatile("mbarrier.init.shared::cta.b64 [%0], %1;" ::"r"(bar), "r"(count)); }
__device__ __forceinline__ void mbar_arrive(uint32_t bar) { asm volatile("mbarrier.arrive.shared::cta.b64 _, [%0];" ::"r"(bar) : "memory"); }
__device__ __forceinline__ void mbar_wait(uint32_t bar, uint32_t parity) {
    asm volatile("{\n.reg .pred p;\nWAIT_LOOP:\n"
                 "mbarrier.try_wait.parity.shared::cta.b64 p, [%0], %1;\n"
                 "@p bra.uni WAIT_DONE;\nbra.uni WAIT_LOOP;\nWAIT_DONE:\n}" ::"r"(bar), "r"(parity) : "memory");
}

__device__ __forceinline__ void mbar_expect_tx(uint32_t bar, uint32_t bytes) {
    asm volatile("mbarrier.arrive.expect_tx.shared::cta.b64 _, [%0], %1;" ::"r"(bar), "r"(bytes) : "memory");
}
__device__ __forceinline__ void tma_load_2d(uint32_t dst, const void* tmap, int c0, int c1, uint32_t bar) {
    asm volatile("cp.async.bulk.tensor.2d.shared::cluster.global.mbarrier::complete_tx::bytes [%0], [%1, {%3, %4}], [%2];"
                 ::"r"(dst), "l"(tmap), "r"(bar), "r"(c0), "r"(c1) : "memory");
}
__device__ __forceinline__ void tma_load_3d(uint32_t dst, const void* tmap, int c0, int c1, int c2, uint32_t bar) {
    asm volatile("cp.async.bulk.tensor.3d.shared::cluster.global.mbarrier::complete_tx::bytes [%0], [%1, {%3, %4, %5}], [%2];"
                 ::"r"(dst), "l"(tmap), "r"(bar), "r"(c0), "r"(c1), "r"(c2) : "memory");
}
__device__ __forceinline__ void fence_async_smem() { asm volatile("fence.proxy.async.shared::cta;" ::: "memory"); }
__device__ __forceinline__ void bulk_load(uint32_t dst, const void* src, uint32_t bytes, uint32_t bar) {
    asm volatile("cp.async.bulk.shared::cluster.global.mbarrier::complete_tx::bytes [%0], [%1], %2, [%3];"
                 ::"r"(dst), "l"(src), "r"(bytes), "r"(bar) : "memory");
}
__device__ __forceinline__ void stsm_x4(uint32_t addr, uint32_t r0, uint32_t r1, uint32_t r2, uint32_t r3) {
    asm volatile("stmatrix.sync.aligned.m8n8.x4.shared.b16 [%0], {%1,%2,%3,%4};" ::"r"(addr), "r"(r0), "r"(r1), "r"(r2), "r"(r3) : "memory");
}
__device__ __forceinline__ void stsm_x4_t(uint32_t addr, uint32_t r0, uint32_t r1, uint32_t r2, uint32_t r3) {
    asm volatile("stmatrix.sync.aligned.m8n8.x4.trans.shared.b16 [%0], {%1,%2,%3,%4};" ::"r"(addr), "r"(r0), "r"(r1), "r"(r2), "r"(r3) : "memory");
}
__device__ __forceinline__ void prefetch_tmap(const void* tmap) { asm volatile("prefetch.tensormap [%0];" ::"l"(tmap) : "memory"); }

__device__ __forceinline__ float2 cexp_at(float wr2, float wi, float p) {
    float er;
    asm("ex2.approx.ftz.f32 %0, %1;" : "=f"(er) : "f"(wr2 * p));
    float th = wi * p;
    const float k = rintf(th * 0.15915494309189535f);
    th = fmaf(k, -6.2831854820251465f, th);
    th = fmaf(k, 1.7484555314695172e-7f, th);
    return make_float2(er * __cosf(th), er * __sinf(th));
}
__device__ __forceinline__ float2 cmul(float2 a, float2 b) {
    return make_float2(fmaf(a.x, b.x, -a.y * b.y), fmaf(a.x, b.y, a.y * b.x));
}
__device__ __forceinline__ float2 csqr(float2 a) { return make_float2(fmaf(a.x, a.x, -a.y * a.y), (a.x + a.x) * a.y); }
__device__ __forceinline__ uint32_t packh(float2 v) {
    uint32_t r;
    asm("cvt.rn.f16x2.f32 %0, %1, %2;" : "=r"(r) : "f"(v.y), "f"(v.x));
    return r;
}
__device__ __forceinline__ void mma_f16(float* d, uint32_t a0, uint32_t a1, uint32_t a2, uint32_t a3, uint32_t b0, uint32_t b1) {
    asm volatile("mma.sync.aligned.m16n8k16.row.col.f32.f16.f16.f32 {%0,%1,%2,%3}, {%4,%5,%6,%7}, {%8,%9}, {%0,%1,%2,%3};"
                 : "+f"(d[0]), "+f"(d[1]), "+f"(d[2]), "+f"(d[3]) : "r"(a0), "r"(a1), "r"(a2), "r"(a3), "r"(b0), "r"(b1));
}

struct KgIn { const bf16 *logA, *Aim, *Cre, *Cim, *logdt, *dsk, *x, *wqkv, *wo; uint4 *tap, *wq, *wop, *halo, *sum; float* csp; };
constexpr int KG_THREADS = NMODE / 2;

constexpr int KG_BUF = 15 * 12288, KG_BAR = KG_BUF + 6 * 5120, KG_SMEM = KG_BAR + 64;
__global__ void __launch_bounds__(512, 1) kgen_kernel(const KgIn in, const __grid_constant__ CUtensorMap tmWq, const __grid_constant__ CUtensorMap tmWo,
                                                        const __grid_constant__ CUtensorMap tmWt) {
    extern __shared__ __align__(1024) uint4 tabs[];
#define KG_ROT 0
    const int lane = threadIdx.x & 31, w16 = (__shfl_sync(~0u, threadIdx.x >> 5, 0) + KG_ROT) & 15, grp = w16 / 3, warp = w16 - 3 * grp;
    const int d = blockIdx.x * 5 + grp, tid = warp * 32 + lane;
    uint4* tab = tabs + grp * (3 * 768);
    SPAN(0, 0); SPAN(0, 1);
    TSTAMPK(0, 0);
    asm volatile("griddepcontrol.launch_dependents;" ::: "memory");
    if (w16 == 15) {
        const uint32_t b0 = smem_u32(tab), wbar = b0 + 6 * 5120;
        const int blk = blockIdx.x, nq = blk < 112 ? 4 : 2, nj = nq + (blk < 64 ? 1 : 2);
        auto fetch = [&](int i) {
            const uint32_t dst = b0 + i * 5120, bar = wbar + 8 * i;
            if (i < nq) {
                const int p = blk + 64 * (i & 2), kb = p / 24;
                mbar_expect_tx(bar, 5120);
                tma_load_3d(dst, &tmWq, 0, kb * 64 + (i & 1) * 32, (p - 24 * kb) * 5, bar);
            } else if (i < nj) {
                const int o = i == nq ? blk : 255 - blk;
                mbar_expect_tx(bar, o < 128 ? 5120 : 2560);
                asm volatile("cp.async.bulk.tensor.5d.shared::cluster.global.mbarrier::complete_tx::bytes [%0], [%1, {%3, %3, %4, %3, %5}], [%2];"
                             ::"r"(dst), "l"(o < 128 ? &tmWo : &tmWt), "r"(bar), "r"(0), "r"((o & 7) * 10 + (o >> 6) * 4), "r"(((o >> 3) & 7) * 5) : "memory");
            }
        };
        const bool one = elect();
        if (one) {
#pragma unroll
            for (int i = 0; i < 6; i++) mbar_init(wbar + 8 * i, 1);
            asm volatile("fence.mbarrier_init.release.cluster;" ::: "memory");
#pragma unroll
            for (int i = 0; i < 6; i++) fetch(i);
        }
        __syncwarp();
#pragma unroll
        for (int i = 1; i <= 5; i++) asm volatile("bar.arrive %0, 128;" ::"r"(i) : "memory");
        if (one) {
#pragma unroll 1
            for (int i = 0; i < nj; i++) {
                const int p = blk + 64 * (i & 2), kb = p / 24, hg = p & 7, sec = (p - 24 * kb) >> 3, o = i == nq ? blk : 255 - blk, cg = (o >> 3) & 7, hb = o & 7;
                const unsigned char* dst = i < nq ? reinterpret_cast<unsigned char*>(in.wq) + (hg * 10 + (hg < 4 ? kb : kb < 5 ? kb + 5 : kb - 5)) * WQ_STAGE + ((i & 1) * 3 + sec) * 5120
                                                  : reinterpret_cast<unsigned char*>(in.wop) + (cg * 8 + (hb == cg ? 0 : hb + (hb < cg))) * WOB + (o >> 6) * 5120;
                mbar_wait(wbar + 8 * i, 0);
                if (i == 0) TSTAMPK(2, (15 - KG_ROT) * 32);
                if (i == 3) TSTAMPK(5, (15 - KG_ROT) * 32);
                asm volatile("cp.async.bulk.global.shared::cta.bulk_group [%0], [%1], %2;" ::"l"(dst), "r"(b0 + i * 5120), "r"(i < nq || o < 128 ? 5120 : 2560) : "memory");
            }
            asm volatile("cp.async.bulk.commit_group;" ::: "memory");
            asm volatile("cp.async.bulk.wait_group.read 0;" ::: "memory");
        }
        TSTAMPK(11, (15 - KG_ROT) * 32);
        return;
    }
    const bf16 pdt = in.logdt[d], pdsk = in.dsk[d];
    const uint32_t pla = reinterpret_cast<const uint32_t*>(in.logA)[d * KG_THREADS + tid], pai = reinterpret_cast<const uint32_t*>(in.Aim)[d * KG_THREADS + tid];
    const uint32_t pcr = reinterpret_cast<const uint32_t*>(in.Cre)[d * KG_THREADS + tid], pci = reinterpret_cast<const uint32_t*>(in.Cim)[d * KG_THREADS + tid];
    const bf16* pfq = tid < 30 ? in.wqkv + (size_t)(d * 30 + tid) * 64 : tid < 40 ? in.wo + (size_t)(d * 10 + tid - 30) * 64 : in.x + (size_t)(d * 32 + tid - 40) * 64;
#define KG_PF 0
    if (tid < (KG_PF == 3 ? 0 : KG_PF ? 40 : 72)) asm volatile("prefetch.global.L2 [%0];" ::"l"(pfq));
    asm volatile("st.global.v4.u32 [%0], {%1,%1,%1,%1};" ::"l"(in.halo + d * 148 + tid), "r"(~0u));
    if (tid < 52) asm volatile("st.global.v4.u32 [%0], {%1,%1,%1,%1};" ::"l"(in.halo + d * 148 + 96 + tid), "r"(~0u));
    else if (w16 == 2) {
        if (lane < 16) in.sum[blockIdx.x * 16 + lane] = make_uint4(0, 0, 0, 0);
        else if (lane < 20) reinterpret_cast<uint32_t*>(in.sum + 2048)[(blockIdx.x * 4 + lane - 16) * FSTR] = 0;
    }
    const uint32_t tw = smem_u32(tab) + warp * 12288;
    const int g = lane >> 2, t = lane & 3;
    const uint32_t sta = tw + lane * 128 + ((2 * (lane & 3) + ((lane >> 2) & 1)) << 4);
    const uint32_t lda = tw + t * 128 + ((g ^ (2 * t)) << 4);
    const uint32_t stb = tw + lane * 8, ldb = tw + g * 512 + (g & 3) * 32 + t * 8;
    auto sts4 = [&](int e, int off, uint32_t a, uint32_t b, uint32_t c, uint32_t dd) {
        asm volatile("st.shared.v4.u32 [%0], {%1,%2,%3,%4};" ::"r"((sta ^ (e << 4)) + off), "r"(a), "r"(b), "r"(c), "r"(dd) : "memory");
    };
    auto lds4 = [&](int sp, int off, uint32_t* r) {
        asm volatile("ld.shared.v4.u32 {%0,%1,%2,%3}, [%4];" : "=r"(r[0]), "=r"(r[1]), "=r"(r[2]), "=r"(r[3]) : "r"((lda ^ ((sp & 1) << 4)) + sp * 512 + off) : "memory");
    };
    const float dt = rbf(expf(bf2f(pdt)));
    float2 C[2], y1[2], z8[2], y128[2];
    float cmax = 0.f;
#pragma unroll
    for (int m = 0; m < 2; m++) {
        const float wr2 = -rbf(expf(__uint_as_float(m ? pla & 0xffff0000u : pla << 16))) * dt * 1.4426950408889634f;
        const float wi = __uint_as_float(m ? pai & 0xffff0000u : pai << 16) * dt;
        C[m] = make_float2(__uint_as_float(m ? pcr & 0xffff0000u : pcr << 16) * dt, -__uint_as_float(m ? pci & 0xffff0000u : pci << 16) * dt);
        cmax = fmaxf(cmax, fmaxf(fabsf(C[m].x), fabsf(C[m].y)));
        y1[m] = cexp_at(wr2, -wi, 1.f); z8[m] = cexp_at(wr2, wi, 8.f); y128[m] = cexp_at(wr2, -wi, 128.f);
    }
    const int ex = min(max((int)(__reduce_max_sync(~0u, __float_as_uint(cmax)) >> 23), 20), 240);
    const float scale = __uint_as_float((uint32_t)(127 + 10 + 127 - ex) << 23), unscale = 2.0f * __uint_as_float((uint32_t)(ex - 10) << 23);
    TSTAMPK(4, 64);
    if (KG_PF >= 2 && tid >= 40 && tid < 72) asm volatile("prefetch.global.L2 [%0];" ::"l"(pfq));
    float k2048 = 0.f;
    float acc[5][4];
#pragma unroll
    for (int j = 0; j < 5; j++)
#pragma unroll
        for (int k = 0; k < 4; k++) acc[j][k] = 0.f;
    uint32_t af[8][4];
    {
        float2 h0[2], h1[2], g0[2], g1[2], g2[2], g2b[2], g3[2], g4[2], y2[2], y4[2];
#pragma unroll
        for (int m = 0; m < 2; m++) {
            h0[m] = make_float2(1.f, 0.f); h1[m] = csqr(csqr(csqr(z8[m])));
            g0[m] = make_float2(C[m].x * scale, C[m].y * scale);
            g1[m] = cmul(g0[m], y128[m]);
            const float2 y256 = csqr(y128[m]), y512 = csqr(y256);
            g2b[m] = g2[m] = cmul(g0[m], y256); g3[m] = cmul(g0[m], y512); g4[m] = cmul(g3[m], y512);
            y2[m] = csqr(y1[m]); y4[m] = csqr(y2[m]);
            const float2 y1024 = csqr(y512);
            k2048 += fmaf(g4[m].x, y1024.x, -g4[m].y * y1024.y);
        }
#pragma unroll
        for (int e = 0; e < 8; e++) {
            sts4(e, 0, packh(h0[0]), packh(h1[0]), packh(h0[1]), packh(h1[1]));
            sts4(e, 4096, packh(g0[0]), packh(g0[1]), packh(g1[0]), packh(g1[1]));
#pragma unroll
            for (int m = 0; m < 2; m++)
                if (e < 7) { h0[m] = e ? cmul(h0[m], z8[m]) : z8[m]; h1[m] = cmul(h1[m], z8[m]); g0[m] = cmul(g0[m], y1[m]); g1[m] = cmul(g1[m], y1[m]); }
            if (e < 5) k2048 += __shfl_xor_sync(~0u, k2048, 1 << e);
        }
        if (KG_PF == 1 && tid >= 40 && tid < 72) asm volatile("prefetch.global.L2 [%0];" ::"l"(pfq));
        __syncwarp();
#pragma unroll
        for (int e = 0; e < 8; e++) {
            uint32_t b[4];
            lds4(e, 0, af[e]); lds4(e, 4096, b);
            sts4(e, 8192, packh(g2[0]), packh(g2[1]), packh((e & 1) ? cmul(g3[0], y4[0]) : g3[0]), packh((e & 1) ? cmul(g3[1], y4[1]) : g3[1]));
            asm volatile("st.shared.v2.u32 [%0], {%1,%2};" ::"r"((stb ^ ((e & 3) << 5)) + e * 512), "r"(packh(g4[0])), "r"(packh(g4[1])) : "memory");
#pragma unroll
            for (int m = 0; m < 2; m++)
                if (e < 7) {
                    g2[m] = e == 3 ? cmul(g2b[m], y128[m]) : cmul(g2[m], y2[m]);
                    if (e & 1) g3[m] = cmul(g3[m], y128[m]);
                    g4[m] = cmul(g4[m], y128[m]);
                }
            mma_f16(acc[0], af[e][0], af[e][1], af[e][2], af[e][3], b[0], b[1]);
            mma_f16(acc[1], af[e][0], af[e][1], af[e][2], af[e][3], b[2], b[3]);
        }
    }
    TSTAMPK(6, 64);
    __syncwarp();
#pragma unroll
    for (int sp = 0; sp < 8; sp++) {
        uint32_t c[4], e0, e1;
        lds4(sp, 8192, c);
        asm volatile("ld.shared.v2.u32 {%0,%1}, [%2];" : "=r"(e0), "=r"(e1) : "r"(ldb ^ (sp << 5)) : "memory");
        mma_f16(acc[2], af[sp][0], af[sp][1], af[sp][2], af[sp][3], c[0], c[1]);
        mma_f16(acc[3], af[sp][0], af[sp][1], af[sp][2], af[sp][3], c[2], c[3]);
        mma_f16(acc[4], af[sp][0], af[sp][1], af[sp][2], af[sp][3], e0, e1);
    }
    {
        float* Pp = reinterpret_cast<float*>(tab + warp * 768);
        auto sw = [](int i) { return i ^ ((i >> 2) & 24); };
#pragma unroll
        for (int h = 0; h < 2; h++) {
            const int b = g + 8 * h;
            *reinterpret_cast<float2*>(Pp + sw(8 * b + 2 * t)) = make_float2(acc[0][2 * h] * unscale, acc[0][2 * h + 1] * unscale);
            *reinterpret_cast<float2*>(Pp + 128 + sw(8 * b + 2 * t)) = make_float2(acc[1][2 * h] * unscale, acc[1][2 * h + 1] * unscale);
            *reinterpret_cast<float2*>(Pp + 256 + sw(4 * b + 2 * (t & 1) + 64 * (t >> 1))) = make_float2(acc[2][2 * h] * unscale, acc[2][2 * h + 1] * unscale);
            *reinterpret_cast<float2*>(Pp + 384 + sw(2 * b + 32 * t)) = make_float2(acc[3][2 * h] * unscale, acc[3][2 * h + 1] * unscale);
            Pp[512 + sw(b + 32 * t)] = acc[4][2 * h] * unscale;
            Pp[512 + sw(b + 32 * t + 16)] = acc[4][2 * h + 1] * unscale;
        }
        if (lane == 0) Pp[640] = k2048 * unscale;
    }
    TSTAMPK(7, 64);
    asm volatile("bar.sync %0, 128;" ::"r"(grp + 1) : "memory");
    TSTAMPK(9, 64);
    const float* Kp = reinterpret_cast<const float*>(tab);
    auto ksum = [&](int i) -> float { return (Kp[i] + Kp[3072 + i]) + Kp[6144 + i]; };
    auto ksum4 = [&](int q) -> float4 {
        q ^= (q >> 2) & 6;
        const float4 a = reinterpret_cast<const float4*>(Kp)[q], b = reinterpret_cast<const float4*>(Kp)[768 + q], c = reinterpret_cast<const float4*>(Kp)[1536 + q];
        return make_float4((a.x + b.x) + c.x, (a.y + b.y) + c.y, (a.z + b.z) + c.z, (a.w + b.w) + c.w);
    };
    {
        uint2* E4 = reinterpret_cast<uint2*>(in.tap + d * 128);
        float4 v = ksum4(tid), u = ksum4(96 + min(tid, 64));
        const float cor = rbf(ksum(tid == 95 ? 384 : 512));
        if (tid == 0) v.x += bf2f(pdsk);
        if (tid == 95) v.w -= cor;
        if (tid == 31) u.w -= cor;
        const uint32_t lo = pack2(v.x, v.y), hi = pack2(v.z, v.w);
        if (tid < 64) {
            E4[6 + tid] = make_uint2(lo, hi);
            E4[(tid < 32 ? 159 : 209 - 32) + tid] = make_uint2(pack2(u.x, u.y), pack2(u.z, u.w));
        } else {
            const uint32_t nx = __shfl_down_sync(~0u, lo, 1);
            in.tap[d * 128 + 35 + tid - 64] = make_uint4(__byte_perm(lo, 0, 0x1010), __byte_perm(lo, hi, 0x5432), __byte_perm(hi, 0, 0x1010), __byte_perm(hi, tid == 95 ? 0u : nx, 0x5432));
            if (tid == 64) E4[241] = make_uint2(pack2(u.x, 0.f), 0u);
        }
    }
    TSTAMPK(10, 64);
    if (warp < (blockIdx.x < 112 ? 2 : 1)) {
        const uint32_t sb = smem_u32(tabs);
        mbar_wait(sb + KG_BAR + 16 * warp, 0); mbar_wait(sb + KG_BAR + 16 * warp + 8, 0);
        uint32_t w[4][4];
        float cs[4] = {0.f, 0.f, 0.f, 0.f};
#pragma unroll
        for (int a = 0; a < 4; a++)
            ldsm_x4_t(w[a], sb + KG_BUF + warp * 10240 + grp * 1024 + ((lane >> 4) * 8 + (lane & 7)) * 32 + ((((lane >> 3) ^ (lane >> 2)) & 1) << 4) + (a >> 1) * 5120 + (a & 1) * 512);
#pragma unroll
        for (int a = 0; a < 4; a++) mma_bf16(cs, w[a][0], w[a][1], w[a][2], w[a][3], 0x3f803f80u, 0x3f803f80u);
        if (t < 2) in.csp[(blockIdx.x + 128 * warp) * 80 + grp * 16 + g + 8 * t] = t ? cs[2] : cs[0];
    }
    SPAN(0, 3);
}

#define CV_SLEEP 40
#define CV_D2 3
#define CV_PDH 12
#define CV_PDF 4
#define CV_HAND 7
constexpr int CV_CPB = 5;
constexpr int CV_THREADS = 512;
constexpr int UPADF = 128;
constexpr int ULEN = UPADF + SEQ;
constexpr int XLEN = SEQ + 16;
constexpr int BX_5 = 0, BX_3 = 3264, BX_9 = 6528, BX_7 = 8960, BX_LEN = 11392;
constexpr int CV_SM_U = 0;
constexpr int CV_SM_T = CV_CPB * ULEN * 2;
constexpr int CV_SM_B = CV_SM_T + CV_CPB * TAPB;
constexpr int CV_SM_X = CV_SM_B + CV_CPB * BX_LEN;
constexpr int CV_SM_Y = (CV_SM_X + CV_CPB * XLEN * 2 + 127) & ~127;
constexpr int CV_SM_CNT = CV_SM_Y + CV_CPB * 8192;
constexpr int CV_SM_O = CV_SM_CNT + 128;
constexpr int CV_SMEM = CV_SM_O + 20480 + CST_EXTRA;
static_assert(ULEN % 128 == 0 && CV_SM_B % 128 == 0 && CV_SM_CNT % 128 == 0, "layout");

__device__ __forceinline__ uint32_t sub2(uint32_t x, uint32_t m) {
    const __nv_bfloat162 d = __hsub2(*reinterpret_cast<const __nv_bfloat162*>(&x), *reinterpret_cast<const __nv_bfloat162*>(&m));
    return *reinterpret_cast<const uint32_t*>(&d);
}
__device__ __forceinline__ uint32_t add2(uint32_t x, uint32_t y) {
    const __nv_bfloat162 d = __hadd2_rn(*reinterpret_cast<const __nv_bfloat162*>(&x), *reinterpret_cast<const __nv_bfloat162*>(&y));
    return *reinterpret_cast<const uint32_t*>(&d);
}
__device__ __forceinline__ void wgmma_fence() { asm volatile("wgmma.fence.sync.aligned;" ::: "memory"); }
__device__ __forceinline__ void wgmma_commit() { asm volatile("wgmma.commit_group.sync.aligned;" ::: "memory"); }
template <int N> __device__ __forceinline__ void wgmma_wait() { asm volatile("wgmma.wait_group.sync.aligned %0;" ::"n"(N) : "memory"); }
__device__ __forceinline__ uint64_t make_desc(uint32_t addr, uint32_t lbo, uint32_t sbo, uint32_t mode) {
    return (uint64_t)((addr & 0x3FFFF) >> 4) | ((uint64_t)(lbo >> 4) << 16) | ((uint64_t)(sbo >> 4) << 32) | ((uint64_t)mode << 62);
}
__device__ __forceinline__ void wgmma_rs128(float (&d)[64], uint2 hi, uint2 lo, uint64_t db, int acc) {
    asm volatile("{\n.reg .pred p;\nsetp.ne.b32 p, %69, 0;\nwgmma.mma_async.sync.aligned.m64n128k16.f32.bf16.bf16 {%0,%1,%2,%3,%4,%5,%6,%7,%8,%9,%10,%11,%12,%13,%14,%15,%16,%17,%18,%19,%20,%21,%22,%23,%24,%25,%26,%27,%28,%29,%30,%31,%32,%33,%34,%35,%36,%37,%38,%39,%40,%41,%42,%43,%44,%45,%46,%47,%48,%49,%50,%51,%52,%53,%54,%55,%56,%57,%58,%59,%60,%61,%62,%63}, {%64,%65,%66,%67}, %68, p, 1, 1, 0;\n}"
                 : "+f"(d[0]), "+f"(d[1]), "+f"(d[2]), "+f"(d[3]), "+f"(d[4]), "+f"(d[5]), "+f"(d[6]), "+f"(d[7]), "+f"(d[8]), "+f"(d[9]), "+f"(d[10]), "+f"(d[11]), "+f"(d[12]), "+f"(d[13]), "+f"(d[14]), "+f"(d[15]), "+f"(d[16]), "+f"(d[17]), "+f"(d[18]), "+f"(d[19]), "+f"(d[20]), "+f"(d[21]), "+f"(d[22]), "+f"(d[23]), "+f"(d[24]), "+f"(d[25]), "+f"(d[26]), "+f"(d[27]), "+f"(d[28]), "+f"(d[29]), "+f"(d[30]), "+f"(d[31]), "+f"(d[32]), "+f"(d[33]), "+f"(d[34]), "+f"(d[35]), "+f"(d[36]), "+f"(d[37]), "+f"(d[38]), "+f"(d[39]), "+f"(d[40]), "+f"(d[41]), "+f"(d[42]), "+f"(d[43]), "+f"(d[44]), "+f"(d[45]), "+f"(d[46]), "+f"(d[47]), "+f"(d[48]), "+f"(d[49]), "+f"(d[50]), "+f"(d[51]), "+f"(d[52]), "+f"(d[53]), "+f"(d[54]), "+f"(d[55]), "+f"(d[56]), "+f"(d[57]), "+f"(d[58]), "+f"(d[59]), "+f"(d[60]), "+f"(d[61]), "+f"(d[62]), "+f"(d[63])
                 : "r"(hi.x), "r"(hi.y), "r"(lo.x), "r"(lo.y), "l"(db), "r"(acc));
}
template <int V> struct Int { __device__ constexpr operator int() const { return V; } };
__device__ __forceinline__ void sts4(uint32_t a, const uint32_t* v) { asm volatile("st.shared.v4.u32 [%0], {%1,%2,%3,%4};" ::"r"(a), "r"(v[0]), "r"(v[1]), "r"(v[2]), "r"(v[3]) : "memory"); }
__device__ __forceinline__ uint32_t lds1(uint32_t a) { uint32_t v; asm volatile("ld.shared.u32 %0, [%1];" : "=r"(v) : "r"(a) : "memory"); return v; }
__device__ __forceinline__ uint4 lds4(uint32_t a) { uint4 v; asm volatile("ld.shared.v4.u32 {%0,%1,%2,%3}, [%4];" : "=r"(v.x), "=r"(v.y), "=r"(v.z), "=r"(v.w) : "r"(a) : "memory"); return v; }
__device__ __forceinline__ void cv_store(unsigned char* p, uint4 x, uint4 y) {
    asm volatile("st.relaxed.gpu.global.v2.u32 [%0], {%1,%2};" ::"l"(p), "r"(add2(x.x, __byte_perm(y.x, y.y, 0x5410))), "r"(add2(x.y, __byte_perm(y.z, y.w, 0x5410))) : "memory");
    asm volatile("st.relaxed.gpu.global.v2.u32 [%0], {%1,%2};" ::"l"(p + 128), "r"(add2(x.z, __byte_perm(y.x, y.y, 0x7632))), "r"(add2(x.w, __byte_perm(y.z, y.w, 0x7632))) : "memory");
}
__device__ __forceinline__ int usw(int ch) { return ch ^ ((ch >> 3) & 1); }
__global__ void __launch_bounds__(CV_THREADS, 1) conv_kernel(int layer, const uint4* __restrict__ piv, const float4* __restrict__ sum, const bf16* __restrict__ x1T,
                                                             bf16* __restrict__ dst, const uint4* __restrict__ tap, const __grid_constant__ CUtensorMap tmOut) {
    extern __shared__ __align__(1024) unsigned char sm[];
    SPAN(3 + 4 * layer, 0);
    bf16* Us = reinterpret_cast<bf16*>(sm + CV_SM_U);
    bf16* Xs = reinterpret_cast<bf16*>(sm + CV_SM_X);
#define CV_IDX int tid; asm volatile("mov.u32 %0, %tid.x;" : "=r"(tid)); const int lane = tid & 31, warp = __shfl_sync(~0u, tid >> 5, 0);
    const int d0 = blockIdx.x * CV_CPB, tile = blockIdx.x; (void)tile;
    const uint32_t cnt = smem_u32(sm + CV_SM_CNT);
    struct Lc { uint32_t a4, a8, uc, ud, y, e4, en, sp, ss; int go; };
    auto lane_consts = [&](int lane, int c) {
        const int mat = lane >> 3, r = lane & 7, g = lane >> 2, ti = lane & 3, e = g - 2 * ti;
        const int j2 = 13 + (r ^ 1) + 8 * (mat >> 1), j3 = j2 + 2, i0 = 8 * (mat & 1);
        const uint32_t sb = smem_u32(sm), oc = sb + usw(16 * (mat >> 1) + 2 * r + (mat & 1)) * 16;
        const Lc l = {sb + CV_SM_B + c * BX_LEN + ((j2 & 1) ? BX_3 + (4 * j2 + i0 + 84) * 2 : BX_5 + (4 * j2 + i0 + 80) * 2),
                      sb + CV_SM_B + c * BX_LEN + ((j3 & 1) ? BX_7 : BX_9) + (8 * j3 + i0 + 136) * 2,
                      oc + CV_SM_U + (c * ULEN + UPADF) * 2, sb + CV_SM_U + (c * ULEN + UPADF) * 2 + usw(16 * mat + 2 * r + 2) * 16, oc + CV_SM_Y + c * 8192,
                      sb + CV_SM_O + 2048 * c + (307 + 2 * g - ti) * 4, sb + CV_SM_T + c * TAPB + (152 + 144 + e) * 8 + 4,
                      e == -5 ? 0x4410u : e == -4 ? 0x1044u : 0x4444u, e == 3 ? 0x4410u : e == 4 ? 0x1044u : 0x4444u,
                      c * XCP * 2 + (lane >> 4) * 256 + (lane & 15) * 8};
        asm volatile("st.shared.u32 [%0], %1;" ::"r"(l.y), "r"(l.a4 ^ l.a8 ^ l.uc ^ l.ud ^ l.e4 ^ l.en ^ l.sp ^ l.ss ^ l.go) : "memory");
        return l;
    };
    unsigned char* const dq = reinterpret_cast<unsigned char*>(dst + (size_t)d0 * XCP);
    auto far = [&](auto T0_, const auto& seq, const Lc& lc, int c, int lane, const uint2 (&f)[20], uint32_t kk) {
        constexpr int T0 = T0_, T1 = T0 + 6, TC = T0 > 7 ? T0 : 7, NS = sizeof(seq) / sizeof(seq[0]), PD = T0 > 7 ? CV_PDH : CV_PDF;
        uint32_t bq[28], yw[4], yz[4], P, S;
        uint4 xv, yv;
        asm("prmt.b32 %0, %1, 0, %2;" : "=r"(P) : "r"(kk), "r"(lc.sp));
        asm("prmt.b32 %0, %1, 0, %2;" : "=r"(S) : "r"(kk), "r"(lc.ss));
#pragma unroll
        for (int k = 0; 2 * k < T1 - TC + 4; k++) ldsm_x4(bq + 4 * k, lc.uc + (TC - 8) * 256 + 512 * k);
#pragma unroll
        for (int k = 0; 4 * k < T1 - TC; k++) ldsm_x4(bq + 20 + 4 * k, lc.ud + (TC - 8) * 256 + 1024 * k);
        CST(3);
        mbar_wait(cnt + 8 * c, 0);
        mbar_wait(cnt + 40, 0);
        CST(4);
        float acc[6][4] = {};
        uint32_t a[PD + 1][4];
#pragma unroll
        for (int i = -PD; i < NS + 3; i++) {
            if (i + PD < NS) ldsm_x4_t(a[(i + PD) % (PD + 1)], seq[i + PD] < 32 ? lc.a4 + (seq[i + PD] - 2) * 128 : lc.a8 + (seq[i + PD] - 34) * 256);
            if (i < 0) continue;
#pragma unroll
            for (int T = T0; T < T1; T++) {
                if (i >= NS) break;
                const int ee = seq[i] < 32 ? 2 * T - 6 - seq[i] : T + 35 - seq[i];
                if (i == 0 && T >= TC) mma_bf16(acc[T - T0], P, 0u, S, P, bq[2 * (T - TC)], bq[2 * (T - TC) + 1]);
                if (i == 1 && T >= TC) mma_bf16_k8(acc[T - T0], 0u, S, bq[20 + T - TC]);
                if (i == (T >= TC ? 2 : 0)) mma_bf16(acc[T - T0], f[19].x, 0u, f[19].y, f[19].x, bq[2 * (T - TC + 4)], bq[2 * (T - TC + 4) + 1]);
                if (seq[i] < 32 ? ee >= 0 && ee <= 9 : ee >= 10) mma_bf16(acc[T - T0], a[i % (PD + 1)][0], a[i % (PD + 1)][1], a[i % (PD + 1)][2], a[i % (PD + 1)][3], f[ee].x, f[ee].y);
            }
#pragma unroll
            for (int k = 0; k < 3; k++) {
                const int o = 256 * T0 + 512 * k;
                auto at = [&](int d) { return i - d >= 0 && i - d < NS && seq[i - d < 0 ? 0 : i - d < NS ? i - d : 0] == 2 * T0 + 4 * k - 4; };
                if (at(CV_D2)) {
                    cv_store(dq + lc.go + o, xv, yv);
                    if (layer > 19 - 2 * k) __trap();
                }
                if (at(-2)) { ldsm_x4_t(yw, lc.y + o); ldsm_x4_t(yz, lc.y + 3584 + o); }
                if (at(1)) {
#pragma unroll
                    for (int q = 0; q < 4; q++) yw[q] = add2(add2(yw[q], yz[q]), pack2(acc[2 * k + (q >> 1)][2 * (q & 1)], acc[2 * k + (q >> 1)][2 * (q & 1) + 1]));
                    stsm_x4_t(lc.y + o, yw[0], yw[1], yw[2], yw[3]);
                    xv = lds4(smem_u32(Xs + c * XLEN) + o + lane * 16);
                    __syncwarp();
                    yv = lds4(smem_u32(sm + CV_SM_Y) + c * 8192 + o + usw(lane) * 16);
                    if (layer > 20 - 2 * k) __trap();
                    if (k == 2) CST(6);
                }
            }
        }
    };
    TSTAMP1X(9, 256);
    if (threadIdx.x >= 256) {
        CV_IDX
        const int t2 = tid - 256, wgu = (warp >> 2) & 1, g = lane >> 2, ti = lane & 3;
        if (t2 == 0) {
            mbar_init(cnt + 48, 1);
            asm volatile("fence.mbarrier_init.release.cluster;" ::: "memory");
            mbar_expect_tx(cnt + 48, CV_CPB * 2048);
            bulk_load(smem_u32(sm + CV_SM_O), tap + d0 * 128, CV_CPB * 2048, cnt + 48);
        } else if (lane == 0) {
            if (warp < 15) mbar_init(cnt + 8 * (warp - 9), warp == 14 ? 8 : 4);
            else if (layer) prefetch_tmap(&tmOut);
        }
        if (t2 < 140) {
            const int k = t2;
            const int off = k < 20 ? CV_SM_B + BX_5 + 8 * k : k < 40 ? CV_SM_B + BX_3 + 8 * (k - 20) : k < 74 ? CV_SM_B + BX_9 + 8 * (k - 40) : k < 108 ? CV_SM_B + BX_7 + 8 * (k - 74) : CV_SM_U + 8 * (k - 108);
            const int str = k < 108 ? BX_LEN : ULEN * 2;
#pragma unroll
            for (int c = 0; c < CV_CPB; c++) *reinterpret_cast<uint2*>(sm + off + c * str) = make_uint2(0, 0);
        }
        fence_async_smem();
        asm volatile("bar.arrive 3, 512;" ::: "memory");
        asm volatile("bar.sync 1, 256;" ::: "memory");
        TSTAMP1X(10, 256);
        asm volatile("setmaxnreg.inc.sync.aligned.u32 168;");
        const int hc = wgu ? warp & 3 : 4;
        const Lc lc = lane_consts(lane, hc);
        const uint32_t* E2[3];
#pragma unroll
        for (int k = 0; k < 3; k++) {
            const int i = min(t2 + 256 * k, 759), h = i / 76;
            E2[k] = reinterpret_cast<const uint32_t*>(sm + CV_SM_O) + 3 + i + (h >> 1) * 360 + (h & 1) * 52;
        }
        mbar_wait(cnt + 48, 0);
        TSTAMP1X(11, 256);
        {
            uint32_t w[3][4];
#pragma unroll
            for (int k = 0; k < 3; k++) { w[k][0] = E2[k][0]; w[k][1] = E2[k][1]; w[k][2] = E2[k][64]; w[k][3] = E2[k][65]; }
#pragma unroll
            for (int k = 0; k < 3; k++)
                *reinterpret_cast<uint4*>(sm + CV_SM_T + min(t2 + 256 * k, 759) * 16) =
                    make_uint4(__byte_perm(w[k][1], w[k][0], 0x7610), __byte_perm(w[k][3], w[k][2], 0x7610), __byte_perm(w[k][1], 0, 0x1032), __byte_perm(w[k][3], 0, 0x1032));
        }
        asm volatile("bar.sync 1, 256;" ::: "memory");
        const uint2* Tc = reinterpret_cast<const uint2*>(sm + CV_SM_T) + 16 + 76 * (warp & 2) + 8 * (warp & 1) + g - 2 * ti;
        uint2 fa[8][2], fn[8][2];
        auto near_taps = [&](uint2 (&f)[8][2], int c) {
#pragma unroll
            for (int m = 0; m < 8; m++) { f[m][0] = Tc[c * (TAPB / 8) + 16 * m]; f[m][1] = Tc[c * (TAPB / 8) + 16 * m - 8]; }
        };
        near_taps(fa, 3 * wgu);
        near_taps(fn, 2 - wgu);
        TSTAMP1X(12, 256); CST(0);
        uint32_t ya = smem_u32(sm + CV_SM_Y) + wgu * 8192 + (warp & 2) * 2048 + usw(2 * lane + (warp & 1)) * 16;
        uint64_t db = make_desc(smem_u32(Us + wgu * ULEN + UPADF), 16, 256, 3);
        if (wgu) asm volatile("bar.sync 6, 384;" ::: "memory");
        int c = wgu;
        auto chain = [&](const uint2 (&f)[8][2], auto&& meanwhile) {
            float acc[64];
            asm volatile("bar.sync %0, %1;" ::"r"(c ? 4 + wgu : 2), "r"(c ? 256 : 384) : "memory");
            TSTAMPC(1 + 3 * c);
            wgmma_fence();
#pragma unroll
            for (int m = 0; m < 8; m++) {
                wgmma_rs128(acc, f[m][0], f[m][1], db - (uint64_t)(2 * m), m);
                if (m == CV_HAND && c < 4) asm volatile("bar.arrive %0, 256;" ::"r"(5 - wgu) : "memory");
            }
            wgmma_commit();
            asm volatile("griddepcontrol.launch_dependents;" ::: "memory");
            TSTAMPC(2 + 3 * c); CST(13 + (c >> 1));
            meanwhile();
            wgmma_wait<0>();
            TSTAMPC(3 + 3 * c); CST(10 + (c >> 1));
            uint32_t w[16];
#pragma unroll
            for (int j = 0; j < 16; j++) w[j] = j ? pack2(acc[4 * j] + acc[4 * j - 2], acc[4 * j + 1] + acc[4 * j - 1]) : pack2(acc[0], acc[1]);
#pragma unroll
            for (int j = 0; j < 16; j += 4) stsm_x4_t(ya + 256 * j, w[j], w[j + 1], w[j + 2], w[j + 3]);
            __syncwarp();
            if (lane == 0) mbar_arrive(cnt + 8 * c);
            c += 2; ya += 16384; db += ULEN / 4;
        };
        const uint32_t e4 = lc.e4, e8 = e4 + 428 - 4 * g;
        uint2 fl[4];
        uint32_t kk;
#pragma unroll 1
        for (;;) {
            if (c != 1) chain(fa, [&] {
                if (c == 3 || warp + c == 12) {
#pragma unroll
                    for (int k = 0; k < 19; k++) (k < 16 ? fn[(k >> 1) & 7][k & 1] : fl[k & 3]) = make_uint2(lds1(k < 10 ? e4 + 32 * k + 16 : e8 + 32 * k - 304), lds1(k < 10 ? e4 + 32 * k : e8 + 32 * k - 320));
                    fl[3] = make_uint2(lds1(lc.en), lds1(lc.en - 64));
                    kk = lds1(smem_u32(sm + CV_SM_O) + 2048 * hc + 1672);
                }
            });
            if (c > 4) break;
            if (c == 2) asm volatile("bar.sync 7, 384;" ::: "memory");
            chain(fn, [&] { if (c == 2) near_taps(fa, 4); });
        }
        TSTAMP1X(6, 256); CST(2);
        if (wgu || warp == 8) {
            constexpr int seq[29] = {5, 6, 32, 7, 33, 8, 34, 9, 35, 10, 36, 11, 12, 13, 14, 15, 16, 17, 37, 18, 38, 19, 20, 21, 39, 22, 40, 23, 24};
            uint2 f[20];
#pragma unroll
            for (int k = 0; k < 20; k++) f[k] = k < 16 ? fn[(k >> 1) & 7][k & 1] : fl[k & 3];
            far(Int<10>(), seq, lc, hc, lane, f, kk);
        }
    } else {
        asm volatile("setmaxnreg.dec.sync.aligned.u32 88;");
        CV_IDX
        const uint4* ppv = piv + tid;
        const float4* psv = sum + tid;
        const uint2* pxv = reinterpret_cast<const uint2*>(x1T + (size_t)d0 * XCP) + (tid >> 4) * 32 + (tid & 15);
        asm volatile("st.shared.u64 [%0], %1;" ::"r"(smem_u32(Xs) + tid * 16), "l"((uint64_t)ppv ^ (uint64_t)psv ^ (uint64_t)pxv) : "memory");
        const int tc = (0x04302100 >> (4 * warp)) & 7;
        const Lc lc = lane_consts(lane, tc);
        pdl_sync();
        SPAN(3 + 4 * layer, 1);
        TSTAMP(0); CST(0);
        if (tid == 0) TSTAMPC(0);
        if (threadIdx.x == 0) { GSTAMP(g_tim, 15); }
        float4 sv[4];
#pragma unroll
        for (int k = 0; k < 4; k++)
            asm volatile("ld.relaxed.gpu.global.v4.f32 {%0,%1,%2,%3}, [%4];" : "=f"(sv[k].x), "=f"(sv[k].y), "=f"(sv[k].z), "=f"(sv[k].w) : "l"(psv + 256 * k) : "memory");
        uint4 pv;
        asm volatile("ld.relaxed.gpu.global.v4.u32 {%0,%1,%2,%3}, [%4];" : "=r"(pv.x), "=r"(pv.y), "=r"(pv.z), "=r"(pv.w) : "l"(ppv) : "memory");
        uint2 xe[CV_CPB], xo[CV_CPB];
#pragma unroll
        for (int c = 0; c < CV_CPB; c++) {
            asm volatile("ld.relaxed.gpu.global.v2.u32 {%0,%1}, [%2];" : "=r"(xe[c].x), "=r"(xe[c].y) : "l"(pxv + c * (XCP / 4)) : "memory");
            asm volatile("ld.relaxed.gpu.global.v2.u32 {%0,%1}, [%2];" : "=r"(xo[c].x), "=r"(xo[c].y) : "l"(pxv + c * (XCP / 4) + 16) : "memory");
        }
        constexpr float idm = 1.0f / DM;
        uint32_t mw[4];
        float rs[8];
#pragma unroll
        for (int k = 0; k < 4; k++) {
            const uint32_t pw = k == 0 ? pv.x : k == 1 ? pv.y : k == 2 ? pv.z : pv.w;
            const float d0_ = sv[k].x * idm, d1_ = sv[k].z * idm;
            mw[k] = pack2(__uint_as_float(pw << 16) + d0_, __uint_as_float(pw & 0xffff0000u) + d1_);
            const uint32_t vr = pack2(fmaxf(fmaf(-d0_, d0_, sv[k].y * idm), 0.f), fmaxf(fmaf(-d1_, d1_, sv[k].w * idm), 0.f));
            const uint32_t ve = pack2(__uint_as_float(vr << 16) + 1e-5f, __uint_as_float(vr & 0xffff0000u) + 1e-5f);
            const uint32_t sd = pack2(sqrt_apx(__uint_as_float(ve << 16)), sqrt_apx(__uint_as_float(ve & 0xffff0000u)));
            rs[2 * k] = rcp_apx(__uint_as_float(sd << 16)); rs[2 * k + 1] = rcp_apx(__uint_as_float(sd & 0xffff0000u));
        }
        if (rs[0] != 123.f) TSTAMP(13);
        const uint32_t ua = smem_u32(Us) + usw(tid + UPADF / 8) * 16;
        uint32_t uw[CV_CPB][4];
#pragma unroll
        for (int c = 0; c < CV_CPB; c++) {
            const uint32_t e0 = sub2(xe[c].x, mw[0]), e1 = sub2(xe[c].y, mw[1]), o0 = sub2(xo[c].x, mw[2]), o1 = sub2(xo[c].y, mw[3]);
            uw[c][0] = pack2(__uint_as_float(e0 << 16) * rs[0], __uint_as_float(o0 << 16) * rs[4]); uw[c][1] = pack2(__uint_as_float(e0 & 0xffff0000u) * rs[1], __uint_as_float(o0 & 0xffff0000u) * rs[5]);
            uw[c][2] = pack2(__uint_as_float(e1 << 16) * rs[2], __uint_as_float(o1 << 16) * rs[6]); uw[c][3] = pack2(__uint_as_float(e1 & 0xffff0000u) * rs[3], __uint_as_float(o1 & 0xffff0000u) * rs[7]);
            asm volatile("st.shared.v4.u32 [%0], {%1,%2,%3,%4};" ::"r"(ua + c * ULEN * 2), "r"(uw[c][0]), "r"(uw[c][1]), "r"(uw[c][2]), "r"(uw[c][3]) : "memory");
            if (c < 2) {
                fence_async_smem();
                asm volatile("bar.arrive %0, 384;" ::"r"(2 + 4 * c) : "memory");
                if (layer > 29 - c) __trap();
            }
        }
        fence_async_smem();
#pragma unroll
        for (int c = 0; c < CV_CPB; c++) *reinterpret_cast<uint4*>(Xs + c * XLEN + tid * 8) = make_uint4(xe[c].x, xe[c].y, xo[c].x, xo[c].y);
        asm volatile("bar.arrive 7, 384;" ::: "memory");
        asm volatile("bar.sync 3, 512;" ::: "memory");
        TSTAMP(1); CST(1);
        {
            auto box = [&](auto c0, auto c1, int chunk, int cb, bool full) {
                const uint32_t ea = smem_u32(Us + cb * ULEN) + usw(chunk + UPADF / 8 + (lane ? 1 : -1)) * 16, bx = smem_u32(sm + CV_SM_B + cb * BX_LEN) + chunk * 16;
                uint32_t lo[CV_CPB][4], hi[CV_CPB][2];
#pragma unroll
                for (int c = c0; c < c1; c++) {
                    lo[c][0] = 0;
#pragma unroll
                    for (int k = 1; k < 4; k++) lo[c][k] = __shfl_up_sync(~0u, uw[c][k], 1);
#pragma unroll
                    for (int k = 0; k < 2; k++) hi[c][k] = __shfl_down_sync(~0u, uw[c][k], 1);
                }
#pragma unroll
                for (int c = c0; c < c1; c++)
                    asm volatile("{\n.reg .pred p, q;\nsetp.eq.s32 p, %7, 0;\nsetp.eq.s32 q, %7, 31;\n@p ld.shared.v4.u32 {%0,%1,%2,%3}, [%6];\n@q ld.shared.v2.u32 {%4,%5}, [%6];\n}"
                                 : "+r"(lo[c][0]), "+r"(lo[c][1]), "+r"(lo[c][2]), "+r"(lo[c][3]), "+r"(hi[c][0]), "+r"(hi[c][1]) : "r"(ea + c * ULEN * 2), "r"(lane) : "memory");
#pragma unroll
                for (int c = c0; c < c1; c++) {
                    const uint32_t e[9] = {lo[c][1], lo[c][2], lo[c][3], uw[c][0], uw[c][1], uw[c][2], uw[c][3], hi[c][0], hi[c][1]};
                    uint32_t o[8], p[8], t[7], b3[5], b5[7];
#pragma unroll
                    for (int i = 0; i < 8; i++) { o[i] = __byte_perm(e[i], e[i + 1], 0x5432); p[i] = add2(e[i], o[i]); }
#pragma unroll
                    for (int i = 0; i < 5; i++) b3[i] = add2(o[i], p[i + 1]);
                    sts4(bx + c * BX_LEN + BX_3 + 160, b3);
#pragma unroll
                    for (int i = 1; i < 7; i++) { t[i] = add2(p[i], p[i + 1]); b5[i] = add2(t[i], e[i + 2]); }
                    sts4(bx + c * BX_LEN + BX_5 + 160, b5 + 2);
                    if (full) {
#pragma unroll
                        for (int i = 1; i < 5; i++) { b3[i] = add2(b3[i], t[i + 2]); t[i] = add2(t[i], b5[i + 2]); }
                        sts4(bx + c * BX_LEN + BX_7 + 272, b3 + 1);
                        sts4(bx + c * BX_LEN + BX_9 + 272, t + 1);
                    }
                }
            };
            auto reload = [&](int c, uint32_t a) { const uint4 v = lds4(a); uw[c][0] = v.x; uw[c][1] = v.y; uw[c][2] = v.z; uw[c][3] = v.w; };
            if (warp >= 6) {
#pragma unroll
                for (int c = 0; c < 3; c++) reload(c, ua - 1024 + (c + 2) * ULEN * 2);
            }
            if (warp >= 4) {
#pragma unroll
                for (int c = 3; c < 5; c++) reload(c, ua - 2048 + c * ULEN * 2);
            }
            box(Int<0>(), Int<3>(), warp < 6 ? tid : tid - 64, warp < 6 ? 0 : 2, warp < 4);
            if (warp >= 4) box(Int<3>(), Int<5>(), tid - 128, 0, true);
            else if (tid >= 128 - CV_CPB) {
                const int c = 127 - tid;
                const uint2 v = *reinterpret_cast<const uint2*>(Us + c * ULEN + UPADF);
                const float s1 = __uint_as_float(v.x << 16), s2 = s1 + __uint_as_float(v.x & 0xffff0000u), s3 = s2 + __uint_as_float(v.y << 16), s4 = s3 + __uint_as_float(v.y & 0xffff0000u);
                unsigned char* bc = sm + CV_SM_B + c * BX_LEN;
                *reinterpret_cast<uint32_t*>(bc + BX_5 + 156) = pack2(s1, s2);
                *reinterpret_cast<uint2*>(bc + BX_7 + 264) = make_uint2(v.x << 16, pack2(s2, s3));
                *reinterpret_cast<uint2*>(bc + BX_9 + 264) = make_uint2(pack2(s1, s2), pack2(s3, s4));
            }
        }
        __syncwarp();
        if (lane == 0) mbar_arrive(cnt + 40);
        TSTAMP(2); CST(2);
        if (layer && blockIdx.x == 0 && tid == 224) g_epoch = ld_epoch();
        __syncwarp();
        if ((0x6e >> warp) & 1) {
            constexpr int seq[16] = {0, 1, 2, 3, 4, 5, 6, 32, 7, 8, 9, 33, 10, 34, 11, 12};
            uint2 f[20];
            mbar_wait(cnt, 0);
            const uint32_t e8 = lc.e4 + 428 - (lane & 28);
#pragma unroll
            for (int k = 0; k < 13; k++) f[k] = make_uint2(lds1(k < 10 ? lc.e4 + 32 * k + 16 : e8 + 32 * k - 304), lds1(k < 10 ? lc.e4 + 32 * k : e8 + 32 * k - 320));
            f[19] = make_uint2(lds1(lc.en), lds1(lc.en - 64));
            far(Int<4>(), seq, lc, tc, lane, f, lds1(smem_u32(sm + CV_SM_O) + 2048 * tc + 1672));
        }
    }
    {
        CV_IDX
        if ((0xc91 >> warp) & 1) {
            const int c = __popc(0xc91 & ((1 << warp) - 1));
            uint4 xv[2], yv[2];
#pragma unroll
            for (int k = 0; k < 2; k++) xv[k] = lds4(smem_u32(Xs + c * XLEN) + 512 * k + lane * 16);
            const uint32_t u0 = lds1(smem_u32(Us + c * ULEN) + (lane == 31 ? UPADF * 2 : 0));
            mbar_wait(cnt + 8 * c, 0);
#pragma unroll
            for (int k = 0; k < 2; k++) yv[k] = lds4(smem_u32(sm + CV_SM_Y) + c * 8192 + 512 * k + usw(lane) * 16);
            const uint4 yz = lds4(smem_u32(sm + CV_SM_Y) + c * 8192 + 4096 + usw(lane) * 16);
            const float kk = __uint_as_float(lds1(smem_u32(sm + CV_SM_O) + 2048 * c + 1272) << 16);
            yv[1].x = add2(yv[1].x, yz.x); yv[1].y = add2(yv[1].y, yz.y); yv[1].z = add2(yv[1].z, yz.z);
            yv[1].w = pack2(fmaf(kk, __uint_as_float(u0 << 16), __uint_as_float(yv[1].w << 16) + __uint_as_float(yz.w << 16)),
                            fmaf(kk, __uint_as_float(u0 << 16) + __uint_as_float(u0 & 0xffff0000u), __uint_as_float(yv[1].w & 0xffff0000u) + __uint_as_float(yz.w & 0xffff0000u)));
#pragma unroll
            for (int k = 0; k < 2; k++) cv_store(dq + c * XCP * 2 + (lane >> 4) * 256 + (lane & 15) * 8 + 512 * k, xv[k], yv[k]);
        }
        TSTAMP(4); CST(8);
        if (layer == 1) {
            const int rb = (blockIdx.x >> 3) + (warp & 8) * 2, cg = blockIdx.x & 7, ch = (tid >> 3) & 31;
            const bf16* src = dst + (size_t)(cg * 80 + ch) * XCP + rb * 64 + (tid & 7) * 8;
            uint32_t v[3][4];
            __syncthreads();
            if (warp & 8) { const uint32_t c0 = clock(); while (clock() - c0 < 300) ; }
            uint32_t todo = (warp & 4) ? 3 : 7;
#pragma unroll 1
            for (int it = 0; it < SPIN_MAX; it++) {
#pragma unroll
                for (int k = 0; k < 3; k++)
                    if (todo >> k & 1)
                        asm volatile("ld.relaxed.gpu.global.v4.u32 {%0,%1,%2,%3}, [%4];" : "=r"(v[k][0]), "=r"(v[k][1]), "=r"(v[k][2]), "=r"(v[k][3]) : "l"(src + k * (32 * XCP)) : "memory");
#pragma unroll
                for (int k = 0; k < 3; k++)
                    if ((todo >> k & 1) && v[k][0] != ~0u && v[k][1] != ~0u && v[k][2] != ~0u && v[k][3] != ~0u) {
                        *reinterpret_cast<uint4*>(sm + (32 * k + ch) * 272 + ((tid & 7) + (warp & 8)) * 16) = make_uint4(v[k][0], v[k][1], v[k][2], v[k][3]);
                        todo ^= 1u << k;
                    }
                if (!todo) break;
                __nanosleep(CV_SLEEP);
            }
            __syncwarp();
            asm volatile("bar.sync %0, 256;" ::"r"(8 + (warp >> 3)) : "memory");
            uint32_t w[12];
#pragma unroll
            for (int k = 0; k < 3; k++) ldsm_x4(&w[4 * k], smem_u32(sm) + min(32 * k + lane, 79) * 272 + warp * 16);
            const uint32_t ot = smem_u32(sm + CV_SM_O) + warp * 1280, oa = ot + (lane & 7) * 160 + (lane >> 3) * 16;
            stsm_x4_t(oa, w[0], w[1], w[2], w[3]);
            stsm_x4_t(oa + 64, w[4], w[5], w[6], w[7]);
            asm volatile("stmatrix.sync.aligned.m8n8.x2.trans.shared.b16 [%0], {%1,%2};" ::"r"(oa + 128), "r"(w[8]), "r"(w[9]) : "memory");
            fence_async_smem();
            __syncwarp();
            if (lane == 0) {
                asm volatile("cp.async.bulk.tensor.3d.global.shared::cta.bulk_group [%0, {%1, %2, %3}], [%4];" ::"l"(&tmOut), "r"(cg * 80), "r"((rb >> 1) * 64 + 8 * (warp & 7)), "r"(rb & 1), "r"(ot) : "memory");
                asm volatile("cp.async.bulk.commit_group;" ::: "memory");
                asm volatile("cp.async.bulk.wait_group.read 0;" ::: "memory");
            }
        }
    }
    TSTAMP(3); CST(9); CST_END;
    GSTAMP(g_tim, 14);
    SPAN(3 + 4 * layer, 3);
}

template <int TA, int TB>
__device__ __forceinline__ void wgmma_n240(float (&d)[120], uint64_t da, uint64_t db, int acc) {
    asm volatile("{\n.reg .pred p;\nsetp.ne.b32 p, %124, 0;\nwgmma.mma_async.sync.aligned.m64n240k16.f32.bf16.bf16 {%0,%1,%2,%3,%4,%5,%6,%7,%8,%9,%10,%11,%12,%13,%14,%15,%16,%17,%18,%19,%20,%21,%22,%23,%24,%25,%26,%27,%28,%29,%30,%31,%32,%33,%34,%35,%36,%37,%38,%39,%40,%41,%42,%43,%44,%45,%46,%47,%48,%49,%50,%51,%52,%53,%54,%55,%56,%57,%58,%59,%60,%61,%62,%63,%64,%65,%66,%67,%68,%69,%70,%71,%72,%73,%74,%75,%76,%77,%78,%79,%80,%81,%82,%83,%84,%85,%86,%87,%88,%89,%90,%91,%92,%93,%94,%95,%96,%97,%98,%99,%100,%101,%102,%103,%104,%105,%106,%107,%108,%109,%110,%111,%112,%113,%114,%115,%116,%117,%118,%119}, %120, %121, p, 1, 1, %122, %123;\n}"
                 : "+f"(d[0]), "+f"(d[1]), "+f"(d[2]), "+f"(d[3]), "+f"(d[4]), "+f"(d[5]), "+f"(d[6]), "+f"(d[7]), "+f"(d[8]), "+f"(d[9]), "+f"(d[10]), "+f"(d[11]), "+f"(d[12]), "+f"(d[13]), "+f"(d[14]), "+f"(d[15]), "+f"(d[16]), "+f"(d[17]), "+f"(d[18]), "+f"(d[19]), "+f"(d[20]), "+f"(d[21]), "+f"(d[22]), "+f"(d[23]), "+f"(d[24]), "+f"(d[25]), "+f"(d[26]), "+f"(d[27]), "+f"(d[28]), "+f"(d[29]), "+f"(d[30]), "+f"(d[31]), "+f"(d[32]), "+f"(d[33]), "+f"(d[34]), "+f"(d[35]), "+f"(d[36]), "+f"(d[37]), "+f"(d[38]), "+f"(d[39]), "+f"(d[40]), "+f"(d[41]), "+f"(d[42]), "+f"(d[43]), "+f"(d[44]), "+f"(d[45]), "+f"(d[46]), "+f"(d[47]), "+f"(d[48]), "+f"(d[49]), "+f"(d[50]), "+f"(d[51]), "+f"(d[52]), "+f"(d[53]), "+f"(d[54]), "+f"(d[55]), "+f"(d[56]), "+f"(d[57]), "+f"(d[58]), "+f"(d[59]), "+f"(d[60]), "+f"(d[61]), "+f"(d[62]), "+f"(d[63]), "+f"(d[64]), "+f"(d[65]), "+f"(d[66]), "+f"(d[67]), "+f"(d[68]), "+f"(d[69]), "+f"(d[70]), "+f"(d[71]), "+f"(d[72]), "+f"(d[73]), "+f"(d[74]), "+f"(d[75]), "+f"(d[76]), "+f"(d[77]), "+f"(d[78]), "+f"(d[79]), "+f"(d[80]), "+f"(d[81]), "+f"(d[82]), "+f"(d[83]), "+f"(d[84]), "+f"(d[85]), "+f"(d[86]), "+f"(d[87]), "+f"(d[88]), "+f"(d[89]), "+f"(d[90]), "+f"(d[91]), "+f"(d[92]), "+f"(d[93]), "+f"(d[94]), "+f"(d[95]), "+f"(d[96]), "+f"(d[97]), "+f"(d[98]), "+f"(d[99]), "+f"(d[100]), "+f"(d[101]), "+f"(d[102]), "+f"(d[103]), "+f"(d[104]), "+f"(d[105]), "+f"(d[106]), "+f"(d[107]), "+f"(d[108]), "+f"(d[109]), "+f"(d[110]), "+f"(d[111]), "+f"(d[112]), "+f"(d[113]), "+f"(d[114]), "+f"(d[115]), "+f"(d[116]), "+f"(d[117]), "+f"(d[118]), "+f"(d[119])
                 : "l"(da), "l"(db), "n"(TA), "n"(TB), "r"(acc));
}

__device__ __forceinline__ void wgmma_n80(float (&d)[40], uint64_t da, uint64_t db, int acc) {
    asm volatile("{\n.reg .pred p;\nsetp.ne.b32 p, %42, 0;\nwgmma.mma_async.sync.aligned.m64n80k16.f32.bf16.bf16 {%0,%1,%2,%3,%4,%5,%6,%7,%8,%9,%10,%11,%12,%13,%14,%15,%16,%17,%18,%19,%20,%21,%22,%23,%24,%25,%26,%27,%28,%29,%30,%31,%32,%33,%34,%35,%36,%37,%38,%39}, %40, %41, p, 1, 1, 0, 1;\n}"
                 : "+f"(d[0]), "+f"(d[1]), "+f"(d[2]), "+f"(d[3]), "+f"(d[4]), "+f"(d[5]), "+f"(d[6]), "+f"(d[7]), "+f"(d[8]), "+f"(d[9]), "+f"(d[10]), "+f"(d[11]), "+f"(d[12]), "+f"(d[13]), "+f"(d[14]), "+f"(d[15]), "+f"(d[16]), "+f"(d[17]), "+f"(d[18]), "+f"(d[19]), "+f"(d[20]), "+f"(d[21]), "+f"(d[22]), "+f"(d[23]), "+f"(d[24]), "+f"(d[25]), "+f"(d[26]), "+f"(d[27]), "+f"(d[28]), "+f"(d[29]), "+f"(d[30]), "+f"(d[31]), "+f"(d[32]), "+f"(d[33]), "+f"(d[34]), "+f"(d[35]), "+f"(d[36]), "+f"(d[37]), "+f"(d[38]), "+f"(d[39])
                 : "l"(da), "l"(db), "r"(acc));
}

constexpr int A1_THREADS = 384;
constexpr int A1_NST = 4;
#define A1_SKEW 8
constexpr int A1_STAGE = 16384 + WQ_STAGE;
constexpr int A1_KVP = 336;
constexpr int A1_SM_KV = 2 * A1_STAGE;
constexpr int A1_SM_BAR = A1_NST * A1_STAGE;
constexpr int A1_SM_RS = A1_SM_BAR + 512;
constexpr int A1_SM_W0 = A1_SM_BAR + 3072, A1_SM_W3 = A1_SM_BAR - 3 * WOB, A1_SM_A1 = 2 * WOB, A1_SM_A0 = A1_SM_A1 + 61440;
constexpr int A1_SM_XA = A1_SM_W0 + 2 * WOB, A1_SM_XB = A1_SM_XA + 2048;
constexpr int A1_SMEM = A1_SM_W0 + 3 * WOB;
static_assert(A1_SM_W3 >= A1_SM_KV + 144 * A1_KVP && A1_SM_W3 % 512 == 0 && A1_SM_A1 % 1024 == 0 && A1_SM_A0 <= A1_SM_KV && A1_SM_A0 + 61440 <= A1_SM_W3 && A1_SMEM <= 232448, "layout");
__device__ __forceinline__ constexpr uint32_t wo_off(int h) { return h * WOB + (h < 3 ? A1_SM_W0 : h < 6 ? A1_SM_W3 - 3 * WOB : -6 * WOB); }
#define A1_FRED "red.relaxed.gpu.global.add.u32"
#define A1_FLD "ld.acquire.gpu.global.u32"
#define ST_SLEEP 20
#define ST_SLEEP0 300
#define WO_LATE bar_done
#define A1_P0 2
#define A1_PW (kb - 2)
#define A1_FSPIN SPIN_MAX
#define A1_FSLEEP 40
#define YT_LAYER 1
#define WOT 352
#define A1_WOAT 6

template <int L>
__device__ __forceinline__ void a1_mainloop(float (&acc)[120], uint32_t sbase, uint32_t bars, int wg, int tile) {
    constexpr int layer = L; (void)layer;
    const uint64_t da0 = L ? make_desc(sbase + wg * 8192, 8192, 1024, 1) : make_desc(sbase + wg * 8192, 16, 1024, 1), db0 = make_desc(sbase + 16384, 1024, 256, 3);
#pragma unroll 1
    for (int t = 0;; t++) {
        const int st = t % A1_NST;
        mbar_wait(bars + 8 * st, (t / A1_NST) & 1);
        if (t == A1_SKEW && wg == 0) mbar_wait(bars + 160, 0);
        TSTAMP3(1 + t);
        wgmma_fence();
#pragma unroll
        for (int kk = 0; kk < 4; kk++) wgmma_n240<L, 1>(acc, da0 + (uint32_t)(st * (A1_STAGE / 16) + kk * (L ? 128 : 2)), db0 + (uint32_t)(st * (A1_STAGE / 16) + (kk >> 1) * (WQ_STAGE / 32) + (kk & 1) * 32), kk ? 1 : t);
        wgmma_commit();
        if (t == 9) break;
        if (t == A1_SKEW - 1 && wg == 0) wgmma_wait<0>(); else wgmma_wait<1>();
        if (t > 0 && (threadIdx.x & 127) == 0) {
            if (t != A1_SKEW || wg) mbar_arrive(bars + 8 * (A1_NST + (t - 1) % A1_NST));
            if (t == A1_SKEW - 1 && wg == 0) mbar_arrive(bars + 8 * (A1_NST + t % A1_NST));
        }
    }
}

__global__ void __launch_bounds__(A1_THREADS, 1) a1_kernel(const int layer, const bf16* __restrict__ x0, const unsigned char* __restrict__ wq, const unsigned char* __restrict__ wo,
                                                           float2* __restrict__ rsum, uint4* __restrict__ of, const __grid_constant__ CUtensorMap tmX,
                                                           const __grid_constant__ CUtensorMap tmR, const __grid_constant__ CUtensorMap tmX1, const __grid_constant__ TileTab tab) {
    extern __shared__ __align__(1024) unsigned char stg[];
    const uint32_t sbase = smem_u32(stg);
    const uint32_t bars = sbase + A1_SM_BAR;
    const uint32_t bar_stat = bars + 64, bar_kv = bars + 72, bar_rd = bars + 168;
    const uint32_t bar_wo = bars + 208, bar_done = bars + 216, bar_pv = bars + 224, bar_kvf = bars + 232, bar_f2 = bars + 248, bar_e2 = bars + 384, que = bars + 448;
    const int tid = threadIdx.x;
    const int w = __shfl_sync(~0u, tid >> 5, 0), wg = w >> 2;
    uint32_t smid, ns;
    asm volatile("mov.u32 %0, %smid;" : "=r"(smid));
    asm volatile("mov.u32 %0, %nsmid;" : "=r"(ns));
    const auto te = tab.e[ns == tab.ns ? smid : 132 + blockIdx.x];
    const int tile = te.tile, mb = te.mb, hg = te.hg;
    float2* rst = reinterpret_cast<float2*>(stg + A1_SM_RS) + 8;
    auto issue_w = [&](int it) { bulk_load(sbase + (it % A1_NST) * A1_STAGE + 16384, wq + te.woff + it * WQ_STAGE, WQ_STAGE, bars + 8 * (it % A1_NST)); };
    auto issue_x = [&](int it, int kb) {
        asm volatile("cp.async.bulk.tensor.5d.shared::cluster.global.mbarrier::complete_tx::bytes [%0], [%1, {%3, %3, %3, %4, %5}], [%2];"
                     ::"r"(sbase + (it % A1_NST) * A1_STAGE), "l"(&tmX), "r"(bars + 8 * (it % A1_NST)), "r"(0), "r"(mb), "r"(kb) : "memory");
    };
    if (w == 8 && tile < 128) {
        const bool one = elect();
        if (one) {
#pragma unroll
            for (int i = 0; i < A1_NST; i++) mbar_init(bars + 8 * i, 1);
            asm volatile("fence.mbarrier_init.release.cluster;" ::: "memory");
        }
        __syncwarp();
        asm volatile("bar.arrive 0, 384;" ::: "memory");
        if (one) {
#define PW asm volatile("griddepcontrol.wait;" ::: "memory");
            if (layer) { issue_w(0); PW issue_x(0, te.kb0); issue_x(1, te.kb0 + 1); }
            else { issue_x(0, te.kb0); issue_x(1, te.kb0 + 1); PW issue_w(0); }
            issue_w(1);
#pragma unroll
            for (int i = 0; i < A1_NST; i++) mbar_expect_tx(bars + 8 * i, A1_STAGE);
            asm volatile("griddepcontrol.launch_dependents;" ::: "memory");
#pragma unroll
            for (int kb = 2; kb < A1_P0; kb++) { issue_x(kb, te.kb0 + kb); issue_w(kb); }
            DBGC(34); DBGV(33, smid); DBGV(40, t_entry); DBGV(30, t_a); DBGV(31, t_b); DBGV(32, t_c); DBGV(38, t_d); DBGV(39, t_e);
        }
    }
    if (tile >= 128) { sm_idle(layer); return; }
    if (wg == 2) {
        if (w != 8) {
            if (tid == 320) { prefetch_tmap(&tmX); prefetch_tmap(&tmR); prefetch_tmap(&tmX1); }
            asm volatile("bar.sync 0, 384;" ::: "memory");
        }
        if (w == 9) {
            asm volatile("bar.arrive 3, 64;" ::: "memory");
            if (layer == 0) pdl_sync();
            float4 a[2] = {};
#pragma unroll
            for (int k = 0; k < 10; k++)
#pragma unroll
                for (int h = 0; h < 2; h++) {
                    const int c4 = min(tid - 288 + 32 * h, 59);
                    const float4 v = __ldcg(reinterpret_cast<const float4*>(g_csp + k * 1920 + hg * 80) + c4 + (c4 / 20) * 140);
                    a[h].x += v.x; a[h].y += v.y; a[h].z += v.z; a[h].w += v.w;
                }
#pragma unroll
            for (int h = 0; h < 2; h++)
#pragma unroll
                for (int k = 0; k < 4; k++) {
                    const float c = 0.5f * (k == 0 ? a[h].x : k == 1 ? a[h].y : k == 2 ? a[h].z : a[h].w), c1 = c - rbf(c), c2 = c1 - rbf(c1);
                    *reinterpret_cast<uint4*>(stg + A1_SM_XB + (4 * min(tid - 288 + 32 * h, 59) + k) * 16) = make_uint4(pack2(c, c1), pack2(c2, 0.f), 0u, 0u);
                }
            fence_async_smem();
            __syncwarp();
            if (tid == 288) mbar_arrive(bar_stat);
#pragma unroll 4
            for (int k = 0; k < 40; k++) asm volatile("st.global.v4.u32 [%0], {%1,%1,%1,%1};" ::"l"(of + (mb * 8 + hg) * 1280 + 32 * k + (tid - 288)), "r"(~0u) : "memory");
            asm volatile("fence.acq_rel.gpu;" ::: "memory");
            asm volatile("fence.proxy.async.global;" ::: "memory");
            __syncwarp();
            if (tid == 288) mbar_arrive(bar_done);
            if (layer == YT_LAYER) {
#pragma unroll 4
                for (int k = tid - 288; k < 5 * XCP / 8; k += 32) asm volatile("st.global.v4.u32 [%0], {%1,%1,%1,%1};" ::"l"(reinterpret_cast<uint4*>(g_yT) + tile * (5 * XCP / 8) + k), "r"(~0u) : "memory");
            }
            TSTAMP1T(9, 288);
        } else if (w == 8) {
            asm volatile("bar.sync 3, 64;" ::: "memory");
            if (elect()) {
#pragma unroll 1
                for (int kb = A1_P0; kb < 10; kb++) {
                    if (kb < A1_NST) mbar_wait(bars + 8 * A1_PW, 0);
                    else {
                        mbar_wait(bars + 8 * (A1_NST + kb % A1_NST), ((kb / A1_NST) - 1) & 1);
                        if (layer && kb < 9) mbar_wait(bar_rd + 8 * (kb - A1_NST), 0);
                        mbar_expect_tx(bars + 8 * (kb % A1_NST), A1_STAGE);
                    }
                    issue_x(kb, kb < 5 ? kb + te.kb0 : kb - te.kb0); issue_w(kb);
                    if (kb == A1_WOAT) {
                        mbar_expect_tx(bar_wo, 8 * WOB);
                        bulk_load(sbase + A1_SM_W0, wo + hg * 8 * WOB, 2 * WOB, bar_wo);
                    }
                }
                TSTAMP1T(6, 256);
                mbar_wait(bars + 8 * (A1_NST + 3), 1);
                bulk_load(sbase + A1_SM_W3, wo + (hg * 8 + 3) * WOB, 3 * WOB, bar_wo);
            }
            __syncwarp();
        } else {
            const int j = tid - 320;
            const uint32_t tag = ld_epoch();
            if (tid == 352) sm_started(layer);
            if (layer == 0) {
                const uint4* src = reinterpret_cast<const uint4*>(x0 + (size_t)(mb * 128 + hg * 16 + (j >> 2)) * DM);
                uint4 v[20];
#pragma unroll
                for (int k = 0; k < 20; k++) v[k] = __ldg(src + (j & 3) + 4 * k);
                const float p0 = __uint_as_float(__shfl_sync(~0u, v[0].x, j & 28) << 16);
                float s[2] = {0.f, 0.f}, q[2] = {0.f, 0.f};
#pragma unroll
                for (int k = 0; k < 20; k++) {
                    const uint32_t w[4] = {v[k].x, v[k].y, v[k].z, v[k].w};
#pragma unroll
                    for (int i = 0; i < 4; i++) {
                        const float a = __uint_as_float(w[i] << 16) - p0, b = __uint_as_float(w[i] & 0xffff0000u) - p0;
                        s[0] += a; s[1] += b; q[0] = fmaf(a, a, q[0]); q[1] = fmaf(b, b, q[1]);
                    }
                }
                float s0 = s[0] + s[1], q0 = q[0] + q[1];
#pragma unroll
                for (int o = 1; o <= 2; o <<= 1) { s0 += __shfl_xor_sync(~0u, s0, o); q0 += __shfl_xor_sync(~0u, q0, o); }
                if ((j & 3) == 0) {
                    const float d = s0 * (1.0f / DM);
                    const uint32_t ms = pack2(p0 + d, sqrt_apx(rbf(rbf(fmaxf(fmaf(-d, d, q0 * (1.0f / DM)), 0.f)) + 1e-5f)));
                    asm volatile("st.global.cg.u64 [%0], %1;" ::"l"(g_rstat + mb * 128 + (j & 4) * 16 + hg * 8 + (j >> 3)), "l"(tagw(ms, tag)) : "memory");
                    g_piv[mb * 128 + hg * 16 + ((j >> 2) & 8) + (j & 4) + ((j >> 3) & 3)] = __ushort_as_bfloat16((unsigned short)ms);
                }
            }
            float o[4];
            int row;
            if (layer == 0) {
                ulonglong2 v;
#pragma unroll 1
                for (int it = 0; it < SPIN_MAX; it++) {
                    v = ld_tag2(reinterpret_cast<const ulonglong2*>(g_rstat + mb * 128) + j);
                    if (tag_ok(v, tag)) break;
                    __nanosleep(100);
                }
                o[0] = __uint_as_float((uint32_t)v.x << 16); o[1] = rcp_apx(__uint_as_float((uint32_t)v.x & 0xffff0000u));
                o[2] = __uint_as_float((uint32_t)v.y << 16); o[3] = rcp_apx(__uint_as_float((uint32_t)v.y & 0xffff0000u));
                row = 2 * j;
            } else {
                const int ch = j & 7, kg = (j >> 3) & 3;
                const unsigned char* src = stg + (j >> 5) * 8192 + (hg & 3) * 2048;
                float s[8], q[8], p0[8];
#pragma unroll
                for (int i = 0; i < 8; i++) { s[i] = 0.f; q[i] = 0.f; }
#pragma unroll 1
                for (int it = 0; it < 5; it++) {
                    uint4 v[4];
                    mbar_wait(bars + 8 * (it % A1_NST), it / A1_NST);
#pragma unroll
                    for (int k = 0; k < 4; k++) v[k] = *reinterpret_cast<const uint4*>(src + (it % A1_NST) * A1_STAGE + (4 * k + kg) * 128 + ((ch ^ ((4 * k + kg) & 7)) << 4));
                    if (it == 0) {
                        const uint4 pv = *reinterpret_cast<const uint4*>(src + (ch << 4));
                        const uint32_t w[4] = {pv.x, pv.y, pv.z, pv.w};
#pragma unroll
                        for (int i = 0; i < 4; i++) { p0[2 * i] = __uint_as_float(w[i] << 16); p0[2 * i + 1] = __uint_as_float(w[i] & 0xffff0000u); }
                    }
                    asm volatile("" :: "r"(v[0].x), "r"(v[1].x), "r"(v[2].x), "r"(v[3].x), "f"(p0[0]) : "memory");
                    __syncwarp();
                    if ((tid & 31) == 0) mbar_arrive(bar_rd + 8 * it);
#pragma unroll
                    for (int k = 0; k < 4; k++) {
                        const uint32_t w[4] = {v[k].x, v[k].y, v[k].z, v[k].w};
#pragma unroll
                        for (int i = 0; i < 4; i++) {
                            const float a = __uint_as_float(w[i] << 16) - p0[2 * i], b = __uint_as_float(w[i] & 0xffff0000u) - p0[2 * i + 1];
                            s[2 * i] += a; s[2 * i + 1] += b; q[2 * i] = fmaf(a, a, q[2 * i]); q[2 * i + 1] = fmaf(b, b, q[2 * i + 1]);
                        }
                    }
                }
#pragma unroll
                for (int i = 0; i < 4; i++) {
                    const bool up = kg & 2;
                    const float ss = __shfl_xor_sync(~0u, up ? s[i] : s[i + 4], 16), qq = __shfl_xor_sync(~0u, up ? q[i] : q[i + 4], 16);
                    s[i] = (up ? s[i + 4] : s[i]) + ss; q[i] = (up ? q[i + 4] : q[i]) + qq; p0[i] = up ? p0[i + 4] : p0[i];
                }
#pragma unroll
                for (int i = 0; i < 2; i++) {
                    const bool up = kg & 1;
                    const float ss = __shfl_xor_sync(~0u, up ? s[i] : s[i + 2], 8), qq = __shfl_xor_sync(~0u, up ? q[i] : q[i + 2], 8);
                    s[i] = (up ? s[i + 2] : s[i]) + ss; q[i] = (up ? q[i + 2] : q[i]) + qq; p0[i] = up ? p0[i + 2] : p0[i];
                }
                uint4* gp = g_halo + 86016 + mb * 512 + j;
                const float d0 = s[0] * (1.0f / 80.0f), d1 = s[1] * (1.0f / 80.0f);
                asm volatile("st.relaxed.gpu.global.v4.f32 [%0], {%1,%2,%3,%4};" ::"l"(gp + hg * 64), "f"(p0[0] + d0), "f"(fmaxf(fmaf(-d0, s[0], q[0]), 0.f)), "f"(p0[1] + d1), "f"(fmaxf(fmaf(-d1, s[1], q[1]), 0.f)) : "memory");
                __nanosleep(ST_SLEEP0);
                uint32_t pw[8][4], todo = 0xff;
#pragma unroll 1
                for (int it = 0; it < SPIN_MAX; it++) {
#pragma unroll
                    for (int k = 0; k < 8; k++)
                        if (todo >> k & 1) asm volatile("ld.relaxed.gpu.global.v4.u32 {%0,%1,%2,%3}, [%4];" : "=r"(pw[k][0]), "=r"(pw[k][1]), "=r"(pw[k][2]), "=r"(pw[k][3]) : "l"(gp + k * 64) : "memory");
#pragma unroll
                    for (int k = 0; k < 8; k++)
                        if (__all_sync(~0u, pw[k][0] != ~0u && pw[k][1] != ~0u && pw[k][2] != ~0u && pw[k][3] != ~0u)) todo &= ~(1u << k);
                    if (!todo) break;
                    __nanosleep(ST_SLEEP);
                }
#pragma unroll
                for (int r = 0; r < 2; r++) {
                    float mean = 0.f, m2 = 0.f;
#pragma unroll
                    for (int k = 0; k < 8; k++) mean += __uint_as_float(pw[k][2 * r]);
                    mean *= 0.125f;
#pragma unroll
                    for (int k = 0; k < 8; k++) {
                        const float dm = __uint_as_float(pw[k][2 * r]) - mean;
                        m2 += fmaf(80.0f * dm, dm, __uint_as_float(pw[k][2 * r + 1]));
                    }
                    o[2 * r] = rbf(mean);
                    o[2 * r + 1] = rcp_apx(rbf(sqrt_apx(rbf(rbf(m2 * (1.0f / DM)) + 1e-5f))));
                }
                row = (j >> 5) * 64 + (j & 7) * 8 + ((j >> 3) & 3) * 2;
                if (hg == 0) *reinterpret_cast<uint32_t*>(g_piv + SEQ + mb * 128 + 2 * (row & 60) + 4 * (row >> 6) + (row & 3)) = __byte_perm(__float_as_uint(o[0]), __float_as_uint(o[2]), 0x7632);
            }
#pragma unroll
            for (int r = 0; r < 2; r++)
                *reinterpret_cast<uint4*>(stg + A1_SM_XA + (row + r) * 16) = make_uint4(__byte_perm(__float_as_uint(-o[2 * r]), 0, 0x3232), __float_as_uint(-o[2 * r]) >> 16, 0u, 0u);
            *reinterpret_cast<float4*>(rst + row + (row >> 6) * 8) = make_float4(o[0], o[1], o[2], o[3]);
            fence_async_smem();
            TSTAMP1T(7, 320);
            if (tid == 320) DBGC(44);
            __syncwarp();
            if ((tid & 31) == 0) mbar_arrive(bar_stat);
        }
        if (tid == 320) DBGCAL(0);
        if (tid == WOT) {
            mbar_wait(WO_LATE, 0);
            mbar_wait(bar_done, 0);
            bulk_load(sbase, wo + (hg * 8 + 6) * WOB, 2 * WOB, bar_wo);
            bulk_load(sbase + A1_SM_W0 + 2 * WOB, wo + (hg * 8 + 2) * WOB, WOB, bar_wo);
        }
        __syncwarp();
#define FWA 11
#define FWB 10
        if (w == FWA || w == FWB) {
            const int cw = w == FWB;
            const uint32_t* fl = reinterpret_cast<const uint32_t*>(rsum + 2 * SEQ) + (((layer * 16 + mb) * 2 + cw) * 8 + (tid & 7)) * FSTR;
            const unsigned char* src = reinterpret_cast<const unsigned char*>(of) + mb * 163840 + cw * 10240 + (tid & 7) * 20480;
            const uint32_t sl = sbase + (cw ? A1_SM_A1 : A1_SM_A0);
            mbar_wait(cw ? bar_done : bar_kvf, 0);
            if ((tid & 31) == 0) {
                mbar_expect_tx(bar_f2 + 64 * cw + 64, 10240);
                tma_load_3d(sl + 51200, &tmR, layer ? 0 : hg * 80, layer ? hg * 80 : mb * 64, layer ? mb * 2 + cw : cw, bar_f2 + 64 * cw + 64);
            }
            __syncwarp();
            uint32_t pend = 0xffu & ~(1u << hg), v = 0;
            const uint32_t bo = wo_off((tid & 7) + ((tid & 7) < hg)) >> 4, lt = (1u << (tid & 31)) - 1;
#pragma unroll 1
            for (int it = 0; pend && it < 2 * SPIN_MAX; it++) {
                if (v != 4 && (pend >> (tid & 31) & 1)) asm volatile(A1_FLD " %0, [%1];" : "=r"(v) : "l"(fl) : "memory");
                uint32_t fr;
                asm volatile("{\n.reg .pred p;\nmbarrier.test_wait.parity.shared::cta.b64 p, [%1], 0;\nselp.b32 %0, 1, 0, p;\n}" : "=r"(fr) : "r"(bar_e2 + 16 * cw + (tid & 1) * 8) : "memory");
                fr = __ballot_sync(~0u, fr);
                uint32_t m = __ballot_sync(~0u, v == 4 || it >= A1_FSPIN) & pend;
                const int q = 8 - __popc(pend) + __popc(m & lt);
                m &= __ballot_sync(~0u, q < ((fr & 2) ? 8 : (fr & 1) ? 7 : 5));
                pend ^= m;
                if (m >> (tid & 31) & 1) DBGC(12 + cw * 8 + (tid & 7));
                if (!m) __nanosleep(A1_FSLEEP);
                else asm volatile("fence.proxy.async.global;" ::: "memory");
                if (m >> (tid & 31) & 1) {
                    bulk_load(q == 7 && !cw ? sbase + A1_SM_W0 : sl + (q < 6 ? q : q - 6) * 10240, src, 10240, bar_f2 + 64 * cw + 8 * q);
                    asm volatile("st.shared.u32 [%0], %1;" ::"r"(que + 32 * cw + 4 * q), "r"(bo) : "memory");
                    mbar_expect_tx(bar_f2 + 64 * cw + 8 * q, 10240);
                    DBGC(44 + cw * 8 + q);
                }
                __syncwarp();
            }
        }
    } else {
        if (tid == 0) {
            mbar_init(bar_stat, 3);
#pragma unroll
            for (int i = 0; i < 8; i++) mbar_init(bar_kv + 8 * i, 1);
            mbar_init(bars + 144, 1);
            mbar_init(bars + 160, 1);
#pragma unroll
            for (int i = 0; i < 5; i++) mbar_init(bar_rd + 8 * i, 2);
            asm volatile("fence.mbarrier_init.release.cluster;" ::: "memory");
        } else if (tid == 32) {
            mbar_init(bar_wo, 1); mbar_init(bar_done, 3); mbar_init(bar_pv, 4); mbar_init(bar_kvf, 8);
#pragma unroll
            for (int i = 0; i < 4; i++) { mbar_init(bar_e2 + 8 * i, i == 1 ? 2 : 1); mbar_init(bars + 8 * (A1_NST + i), 2); }
            asm volatile("fence.mbarrier_init.release.cluster;" ::: "memory");
        } else if (tid == 96) {
#pragma unroll
            for (int i = 0; i < 4; i++) mbar_init(bars + 416 + 8 * i, 1);
            asm volatile("fence.mbarrier_init.release.cluster;" ::: "memory");
        } else if (tid == 64) {
#pragma unroll
            for (int i = 1; i <= 16; i++) mbar_init(bar_f2 + 8 * i, 1);
            asm volatile("fence.mbarrier_init.release.cluster;" ::: "memory");
        }
        asm volatile("bar.sync 0, 384;" ::: "memory");
        SPAN(1 + 4 * layer, 0);
        constexpr int on = 1;
        float acc[120];
        const int lane = tid & 31, warp = w & 7, g = lane >> 2, t = lane & 3;
        if (on) {
            SPAN(1 + 4 * layer, 1);
            TSTAMP1(0);
            if (threadIdx.x == 0) { GSTAMP(g_tim1, 15); }
            TSTAMP3(0);
            if (tid == 0) TSTAMP2(0);
            TSTAMP4(0);
            if (tid == 0) DBGC(60);
            if (layer == 0) a1_mainloop<0>(acc, sbase, bars, wg, tile); else a1_mainloop<1>(acc, sbase, bars, wg, tile);
            uint32_t ok;
            asm volatile("{\n.reg .pred p;\nmbarrier.test_wait.parity.shared::cta.b64 p, [%1], 0;\nselp.b32 %0, 1, 0, p;\n}" : "=r"(ok) : "r"(bar_stat) : "memory");
            if (tid == 128 && !ok) mbar_arrive(bars + 160);
            __syncwarp();
            mbar_wait(bar_stat, 0);
            wgmma_fence();
            wgmma_n240<0, 0>(acc, make_desc(sbase + A1_SM_XA + wg * 1024, 0, 128, 0), make_desc(sbase + A1_SM_XB, 0, 128, 0), 1);
            wgmma_commit();
            if (tid == 128 && ok) mbar_arrive(bars + 160);
            mbar_wait(bars + 8 * (A1_NST + 3), 1);
        }
        const float2* rw = rst + 16 * warp + 8 * wg;
        const float rb0 = rw[g + 8].y, ra = rw[g].y * 0.22360679774997896f, rb = rb0 * 0.22360679774997896f;
        wgmma_wait<0>();
        if ((tid & 127) == 0) mbar_arrive(bar_done);
        TSTAMP1(2);
        TSTAMP1T(13, 224);
        if ((tid & 127) == 0) DBGC(62 - wg);
        uint32_t f[2][30];
#pragma unroll
        for (int j = 10; j < 30; j++) f[1][j] = pack2(acc[4 * j + 2], acc[4 * j + 3]);
        if ((warp & 3) == 3) {
            uint4* hout = g_halo + (((layer * 16 + mb) * 8 + hg) * 2 + wg) * 168;
#pragma unroll
            for (int j = 0; j < 20; j += 4)
                asm volatile("st.relaxed.gpu.global.v4.u32 [%0], {%1,%2,%3,%4};" ::"l"(hout + 8 * j + lane), "r"(f[1][10 + j]), "r"(f[1][11 + j]), "r"(f[1][12 + j]), "r"(f[1][13 + j]) : "memory");
            if (t == 0) asm volatile("st.relaxed.gpu.global.f32 [%0], %1;" ::"l"(reinterpret_cast<float*>(hout + 160) + g), "f"(rb0) : "memory");
        }
        TSTAMP1T(12, 224);
        const uint32_t kvw = sbase + A1_SM_KV + (16 * warp + 8 * wg) * A1_KVP;
        const uint32_t mrow = kvw + (lane & 7) * A1_KVP + (lane >> 3) * 16;
#pragma unroll
        for (int j = 0; j < 20; j += 4) stsm_x4(mrow + 16 * A1_KVP + 16 * j, f[1][10 + j], f[1][11 + j], f[1][12 + j], f[1][13 + j]);
        __syncwarp();
        if (lane == 0 && (warp & 3) != 3) mbar_arrive(bar_kv + 8 * (warp + 1));
#pragma unroll
        for (int j = 0; j < 30; j++) f[0][j] = pack2(acc[4 * j], acc[4 * j + 1]);
        stsm_x4(mrow + 8 * A1_KVP + 160, f[0][20], f[0][21], f[0][22], f[0][23]);
        stsm_x4(mrow + 8 * A1_KVP + 224, f[0][24], f[0][25], f[0][26], f[0][27]);
        asm volatile("stmatrix.sync.aligned.m8n8.x2.shared.b16 [%0], {%1,%2};" ::"r"(mrow + 8 * A1_KVP + 288), "r"(f[0][28]), "r"(f[0][29]) : "memory");
#pragma unroll
        for (int j = 0; j < 10; j++) f[1][j] = pack2(acc[4 * j + 2], acc[4 * j + 3]);
        __syncwarp();
        uint32_t vb[10][2], vp[12], kp[12];
#pragma unroll
        for (int j = 0; j < 10; j += 2) ldsm_x4_t(&vb[j][0], kvw + (8 + (lane & 15)) * A1_KVP + 160 + (lane >> 4) * 16 + 16 * j);
        const bool up0 = 2 * t > g, up1 = 2 * t + 1 > g, edge = (mb | (warp & 3)) == 0;
        float rk[4];
        auto above = [&]() {
            mbar_wait(bar_kv + 8 * warp, 0);
#pragma unroll
            for (int j = 0; j < 12; j += 4) ldsm_x4(&kp[j], mrow + 16 * j);
            rk[0] = rw[2 * t - (up0 ? 8 : 0)].y; rk[1] = rw[2 * t + 1 - (up1 ? 8 : 0)].y;
#pragma unroll
            for (int j = 0; j < 12; j += 4) ldsm_x4_t(&vp[j], mrow + 160 + 16 * j - (j == 8 ? (lane & 16) * 2 : 0));
            __syncwarp();
            if (lane == 0) mbar_arrive(bar_kvf);
        };
        auto halo = [&]() {
            if (lane == 0) mbar_arrive(bar_kvf);
            const uint4* hin = g_halo + (((layer * 16 + mb - 1) * 8 + hg) * 2 + wg) * 168;
            uint32_t hv[22] = {};
            rk[0] = rw[2 * t].y; rk[1] = rw[2 * t + 1].y;
            if (mb > 0) {
#pragma unroll 1
                for (int it = 0; it < SPIN_MAX; it++) {
#pragma unroll
                    for (int k = 0; k < 20; k += 4)
                        asm volatile("ld.relaxed.gpu.global.v4.u32 {%0,%1,%2,%3}, [%4];" : "=r"(hv[k]), "=r"(hv[k + 1]), "=r"(hv[k + 2]), "=r"(hv[k + 3]) : "l"(hin + 8 * k + lane) : "memory");
                    asm volatile("ld.relaxed.gpu.global.v2.u32 {%0,%1}, [%2];" : "=r"(hv[20]), "=r"(hv[21]) : "l"(reinterpret_cast<const uint2*>(hin + 160) + t) : "memory");
                    uint32_t m = max(hv[20], hv[21]);
#pragma unroll
                    for (int k = 0; k < 20; k += 2) m = __vimax3_u32(m, hv[k], hv[k + 1]);
                    if (!__any_sync(~0u, m == ~0u)) break;
                }
            }
            if (tid == 0) mbar_arrive(bars + 144);
            if (lane == 0) DBGC(52 - 16 * wg);
#pragma unroll
            for (int j = 0; j < 10; j++) {
                kp[j] = hv[j];
                asm volatile("movmatrix.sync.aligned.m8n8.trans.b16 %0, %1;" : "=r"(vp[j]) : "r"(hv[10 + j]));
            }
            if (up0) rk[0] = __uint_as_float(hv[20]);
            if (up1) rk[1] = __uint_as_float(hv[21]);
        };
        rk[2] = rw[2 * t + (up0 ? 0 : 8)].y; rk[3] = rw[2 * t + 1 + (up1 ? 0 : 8)].y;
        uint32_t qs[4][2];
#pragma unroll
        for (int h = 0; h < 4; h++) {
            qs[h][0] = (t >> 1) == (h & 1) ? f[0][5 * (h >> 1) + 2] : 0u; qs[h][1] = (t >> 1) == (h & 1) ? f[1][5 * (h >> 1) + 2] : 0u;
            asm volatile("" : "+r"(qs[h][0]), "+r"(qs[h][1]));
        }
#pragma unroll
        for (int j = 0; j < 10; j++) asm volatile("" : "+r"(f[0][j]), "+r"(f[1][j]), "+r"(f[0][10 + j]));
        if (warp & 3) above(); else if (wg) halo();
        TSTAMP1T(10, 64);
        if (warp && !wg) mbar_wait(bars + 416 + 8 * warp, 0);
        float sc[4][3][4];
#pragma unroll
        for (int h = 0; h < 4; h++) {
            const int jb = 5 * (h >> 1) + 3 * (h & 1), js = 5 * (h >> 1) + 2;
#pragma unroll
            for (int nt = 1; nt < 3; nt++) {
#pragma unroll
                for (int e = 0; e < 4; e++) sc[h][nt][e] = 0.f;
                mma_bf16(sc[h][nt], f[0][jb], f[1][jb], f[0][jb + 1], f[1][jb + 1], f[nt - 1][10 + jb], f[nt - 1][11 + jb]);
                mma_bf16_k8(sc[h][nt], qs[h][0], qs[h][1], f[nt - 1][10 + js]);
            }
        }
        if (warp == 0) halo();
        TSTAMP1(8);
#pragma unroll
        for (int h = 0; h < 4; h++) {
            const int jb = 5 * (h >> 1) + 3 * (h & 1), js = 5 * (h >> 1) + 2;
#pragma unroll
            for (int e = 0; e < 4; e++) sc[h][0][e] = 0.f;
            mma_bf16(sc[h][0], f[0][jb], f[1][jb], f[0][jb + 1], f[1][jb + 1], kp[jb], kp[jb + 1]);
            mma_bf16_k8(sc[h][0], qs[h][0], qs[h][1], kp[js]);
        }
        TSTAMP1T(3, 64);
        float p[4][4], sum[4][2];
        uint32_t lg[4][2], mx[4];
        const float rl[4] = {rk[0] * ra, rk[1] * ra, rk[2] * rb, rk[3] * rb};
        auto max2 = [](uint32_t a, uint32_t b) { uint32_t r; asm("max.bf16x2 %0, %1, %2;" : "=r"(r) : "r"(a), "r"(b)); return r; };
#pragma unroll
        for (int h = 0; h < 4; h++) {
            lg[h][0] = pack2((up0 ? sc[h][0][0] : sc[h][1][0]) * rl[0], (up0 ? sc[h][1][2] : sc[h][2][2]) * rl[2]);
            lg[h][1] = pack2((up1 ? sc[h][0][1] : sc[h][1][1]) * rl[1], (up1 ? sc[h][1][3] : sc[h][2][3]) * rl[3]);
            if (edge) {
                if (up0) lg[h][0] = __byte_perm(lg[h][0], 0xce6eu, 0x3254);
                if (up1) lg[h][1] = __byte_perm(lg[h][1], 0xce6eu, 0x3254);
            }
            mx[h] = max2(lg[h][0], lg[h][1]);
        }
#pragma unroll
        for (int o = 1; o <= 2; o <<= 1)
#pragma unroll
            for (int h = 0; h < 4; h++) mx[h] = max2(mx[h], __shfl_xor_sync(~0u, mx[h], o));
#pragma unroll
        for (int h = 0; h < 4; h++)
#pragma unroll
            for (int r = 0; r < 2; r++) {
                const float m = __uint_as_float(r ? mx[h] & 0xffff0000u : mx[h] << 16);
#pragma unroll
                for (int e = 0; e < 2; e++)
                    asm("ex2.approx.ftz.f32 %0, %1;" : "=f"(p[h][2 * r + e]) : "f"((__uint_as_float(r ? lg[h][e] & 0xffff0000u : lg[h][e] << 16) - m) * 1.4426950408889634f));
                sum[h][r] = p[h][2 * r] + p[h][2 * r + 1];
            }
#pragma unroll
        for (int o = 1; o <= 2; o <<= 1)
#pragma unroll
            for (int h = 0; h < 4; h++)
#pragma unroll
                for (int r = 0; r < 2; r++) sum[h][r] += __shfl_xor_sync(~0u, sum[h][r], o);
        TSTAMP1T(5, 64);
        const uint32_t mu = (up0 ? 0xffffu : 0u) | (up1 ? 0xffff0000u : 0u);
        uint32_t ob[10][2];
#pragma unroll
        for (int P = 0; P < 2; P++) {
            float os[2][4];
#pragma unroll
            for (int e = 0; e < 2; e++) {
                const int h = 2 * P + e;
                const float i0 = rcp_apx(sum[h][0]), i1 = rcp_apx(sum[h][1]);
                const uint32_t w0 = pack2(p[h][0] * rk[0] * i0, p[h][1] * rk[1] * i0), w1 = pack2(p[h][2] * rk[2] * i1, p[h][3] * rk[3] * i1);
#pragma unroll
                for (int dt = 0; dt < 3; dt++) {
                    const int j = 5 * P + (dt < 2 ? 3 * e + dt : 2);
                    float o[4] = {0.f, 0.f, 0.f, 0.f};
                    mma_bf16(o, w0 & ~mu, w1 & mu, 0u, w1 & ~mu, vb[j][0], vb[j][1]);
                    mma_bf16_k8(o, w0 & mu, 0u, vp[j]);
                    if (dt < 2) { ob[j][0] = pack2(o[0], o[1]); ob[j][1] = pack2(o[2], o[3]); }
                    else { os[e][0] = o[0]; os[e][1] = o[1]; os[e][2] = o[2]; os[e][3] = o[3]; }
                }
            }
#pragma unroll
            for (int k = 0; k < 4; k++) os[0][k] = t < 2 ? os[0][k] : os[1][k];
            ob[5 * P + 2][0] = pack2(os[0][0], os[0][1]); ob[5 * P + 2][1] = pack2(os[0][2], os[0][3]);
        }
        const uint32_t sl = sbase + (wg ? A1_SM_A1 : A1_SM_A0);
        const uint32_t o0 = (warp & 3) * 2048 + g * 64 + ((t ^ (g >> 1)) << 4), o1 = 8192 + (warp & 3) * 512 + g * 32 + ((t ^ ((g >> 2) << 1)) << 3);
        mbar_wait(bar_done, 0);
        if (wg == 0) mbar_wait(bar_kvf, 0);
#pragma unroll
        for (int h = 0; h < 2; h++) {
            asm volatile("st.shared.v4.u32 [%0], {%1,%2,%3,%4};" ::"r"(sl + o0 + h * 1024), "r"(ob[0][h]), "r"(ob[1][h]), "r"(ob[2][h]), "r"(ob[3][h]) : "memory");
            asm volatile("st.shared.v4.u32 [%0], {%1,%2,%3,%4};" ::"r"(sl + o0 + h * 1024 + 512), "r"(ob[4][h]), "r"(ob[5][h]), "r"(ob[6][h]), "r"(ob[7][h]) : "memory");
            asm volatile("st.shared.v2.u32 [%0], {%1,%2};" ::"r"(sl + o1 + h * 256), "r"(ob[8][h]), "r"(ob[9][h]) : "memory");
        }
        if (wg && lane == 0) mbar_arrive(bars + 384 + 8 * warp);
        fence_async_smem();
        __syncwarp();
        TSTAMP1T(4, 64);
        TSTAMP1(1);
        TSTAMP2(1);
        const unsigned char* ot = reinterpret_cast<const unsigned char*>(of) + mb * 163840 + wg * 10240;
        if (lane == 0) {
            asm volatile("cp.async.bulk.global.shared::cta.bulk_group [%0], [%1], 2048;" ::"l"(ot + hg * 20480 + (warp & 3) * 2048), "r"(sl + (warp & 3) * 2048) : "memory");
            asm volatile("cp.async.bulk.global.shared::cta.bulk_group [%0], [%1], 512;" ::"l"(ot + hg * 20480 + 8192 + (warp & 3) * 512), "r"(sl + 8192 + (warp & 3) * 512) : "memory");
            asm volatile("cp.async.bulk.commit_group;" ::: "memory");
            if (wg == 0) mbar_arrive(bar_pv);
            asm volatile("cp.async.bulk.wait_group 0;" ::: "memory");
            asm volatile(A1_FRED " [%0], 1;" ::"l"(reinterpret_cast<uint32_t*>(rsum + 2 * SEQ) + (((layer * 16 + mb) * 2 + wg) * 8 + hg) * FSTR) : "memory");
            DBGC(4 + warp);
        }
        TSTAMP4(11);
        float ac2[40];
        const uint64_t db0 = make_desc(sbase, 1024, 256, 3), db1 = make_desc(sbase + 10240, 512, 256, 3), da0 = make_desc(sl, 16, 1024, 2), da1 = make_desc(sl + 8192, 16, 256, 3);
        const uint32_t o7 = wg ? 640 : (A1_SM_W0 - A1_SM_A0) >> 4;
        const uint32_t trow = ((lane & 7) + 8 * (lane >> 4)) * 128 + (((2 * (warp & 3) + ((lane >> 3) & 1)) ^ (lane & 7)) << 4);
        uint32_t xr[10][2];
        mbar_wait(bar_f2 + 64 * wg + 64, 0);
        if (layer == 0) {
#pragma unroll
            for (int j = 0; j < 10; j += 2) ldsm_x4(&xr[j][0], sl + 51200 + (16 * (warp & 3) + (lane & 15)) * 160 + (lane >> 4) * 16 + 16 * j);
        } else {
#pragma unroll
            for (int j = 0; j < 10; j += 2) ldsm_x4_t(&xr[j][0], sl + 51200 + trow + 1024 * j);
        }
        const uint32_t ri = __shfl_sync(~0u, layer * SEQ + (wg * 2 + ((g >> 1) & 1)) * 512 + (mb * 16 + 4 * (warp & 3) + (g >> 2)) * 2 + (g & 1), lane);
        mbar_wait(bar_wo, 0);
        if (wg) mbar_wait(bar_pv, 0);
        if (wg) asm volatile("bar.sync 2, 128;" ::: "memory"); else asm volatile("bar.sync 1, 128;" ::: "memory");
        TSTAMP2(2);
#pragma unroll
        for (int q = 0; q < 8; q++) {
            uint32_t bo = wo_off(0) >> 4;
            if (q) {
                mbar_wait(bar_f2 + 64 * wg + 8 * q, 0);
                asm volatile("ld.shared.u32 %0, [%1];" : "=r"(bo) : "r"(que + 32 * wg + 4 * q) : "memory");
                bo = __shfl_sync(~0u, bo, 0);
                TSTAMP4(q);
                if (q == 1 && (tid & 127) == 0) DBGC(29 + 8 * wg);
            }
            wgmma_fence();
#pragma unroll
            for (int j = 0; j < 5; j++) wgmma_n80(ac2, (j < 4 ? da0 : da1) + (q == 7 ? o7 : 0u) + (uint64_t)((q < 6 ? q * 640 : 0) + (j & 2) * 16 + (j & 1) * 2), (j < 4 ? db0 : db1) + bo + (uint64_t)((j & 2) * 160 + (j & 1) * 32), j || q);
            wgmma_commit();
            if (q == 0) {
                wgmma_wait<0>();
                if ((tid & 127) == 0) { mbar_arrive(bar_e2 + 16 * wg); mbar_arrive(bar_e2 + 8); }
            }
            if (q == 2 && wg) {
                wgmma_wait<1>();
                if (tid == 128) mbar_arrive(bar_e2 + 24);
            }
        }
        if ((tid & 127) == 0) DBGC(28 + wg * 8 + 7);
        TSTAMP2(3);
        wgmma_wait<0>();
        TSTAMP2(4);
        if (__any_sync(~0u, ac2[0] != ac2[0] || ac2[2] != ac2[2])) {
#pragma unroll
            for (int i = 0; i < 40; i++) ac2[i] = 0.f;
            uint32_t a[20], an[20];
            auto lda = [&](uint32_t (&r)[20], int h) {
#pragma unroll
                for (int u = 0; u < 4; u++)
                    asm volatile("ld.relaxed.gpu.global.v4.u32 {%0,%1,%2,%3}, [%4];" : "=r"(r[4 * u]), "=r"(r[4 * u + 1]), "=r"(r[4 * u + 2]), "=r"(r[4 * u + 3]) : "l"(ot + h * 20480 + o0 + u * 512) : "memory");
#pragma unroll
                for (int u = 0; u < 2; u++)
                    asm volatile("ld.relaxed.gpu.global.v2.u32 {%0,%1}, [%2];" : "=r"(r[16 + 2 * u]), "=r"(r[17 + 2 * u]) : "l"(ot + h * 20480 + o1 + u * 256) : "memory");
            };
            lda(an, 0);
#pragma unroll 5
            for (int k = lane; k < WOB / 16; k += 32)
                reinterpret_cast<uint4*>(stg + (sl - sbase))[k] = __ldcg(reinterpret_cast<const uint4*>(wo + hg * 8 * WOB) + k);
            __syncwarp();
#pragma unroll 1
            for (int h = 0; h < 8; h++) {
#pragma unroll 1
                for (int it = 0; it < SPIN_MAX; it++) {
                    uint32_t m = 0;
#pragma unroll
                    for (int k = 0; k < 20; k += 2) m = __vimax3_u32(m, an[k], an[k + 1]);
                    if (!__any_sync(~0u, m == ~0u)) break;
                    lda(an, h);
                }
#pragma unroll
                for (int k = 0; k < 20; k++) a[k] = an[k];
                lda(an, min(h + 1, 7));
                const uint32_t bp = h == hg ? sl : sbase + wo_off(h + (h < hg));
                const int r0 = 8 * ((lane & 7) >> 1) + 2 * (lane >> 3) + (lane & 1), r2 = 4 * ((lane & 7) >> 1) + 2 * ((lane >> 3) & 1) + (lane & 1);
#pragma unroll
                for (int n = 0; n < 10; n++) {
                    uint32_t b[12];
                    ldsm_x4_t(b, bp + (n >> 1) * 1024 + r0 * 32 + (((n ^ (r0 >> 2)) & 1) << 4));
                    ldsm_x4_t(b + 4, bp + 5120 + (n >> 1) * 1024 + r0 * 32 + (((n ^ (r0 >> 2)) & 1) << 4));
                    ldsm_x4_t(b + 8, bp + 10240 + (n >> 1) * 512 + r2 * 32 + (((n ^ (r2 >> 2)) & 1) << 4));
                    mma_bf16(ac2 + 4 * n, a[0], a[8], a[1], a[9], b[0], b[1]); mma_bf16(ac2 + 4 * n, a[2], a[10], a[3], a[11], b[2], b[3]);
                    mma_bf16(ac2 + 4 * n, a[4], a[12], a[5], a[13], b[4], b[5]); mma_bf16(ac2 + 4 * n, a[6], a[14], a[7], a[15], b[6], b[7]);
                    mma_bf16(ac2 + 4 * n, a[16], a[18], a[17], a[19], b[8], b[9]);
                }
            }
        }
#pragma unroll
        for (int j = 0; j < 10; j++)
#pragma unroll
            for (int hh = 0; hh < 2; hh++) {
                const uint32_t a = pack2(ac2[4 * j + 2 * hh], ac2[4 * j + 2 * hh + 1]);
                const __nv_bfloat162 r = __hadd2_rn(*reinterpret_cast<const __nv_bfloat162*>(&xr[j][hh]), *reinterpret_cast<const __nv_bfloat162*>(&a));
                xr[j][hh] = *reinterpret_cast<const uint32_t*>(&r);
            }
        const uint32_t so = sl + 30720;
#pragma unroll
        for (int j = 0; j < 10; j += 2) stsm_x4_t(so + trow + 1024 * j, xr[j][0], xr[j][1], xr[j + 1][0], xr[j + 1][1]);
        fence_async_smem();
        if (wg) asm volatile("bar.sync 2, 128;" ::: "memory"); else asm volatile("bar.sync 1, 128;" ::: "memory");
        TSTAMP2(5);
        if ((tid & 127) == 0) {
            asm volatile("cp.async.bulk.tensor.2d.global.shared::cta.bulk_group [%0, {%1, %2}], [%3];" ::"l"(&tmX1), "r"(mb * 128 + 64 * wg), "r"(hg * 80), "r"(so) : "memory");
            asm volatile("cp.async.bulk.commit_group;" ::: "memory");
        }
        __syncwarp();
        const float p0 = *(volatile const float*)&rw[g].x, p1 = *(volatile const float*)&rw[g + 8].x;
        float s[3][4] = {};
        const uint32_t pp[2] = {__byte_perm(__float_as_uint(p0), 0, 0x3232), __byte_perm(__float_as_uint(p1), 0, 0x3232)};
#pragma unroll
        for (int j = 0; j < 10; j += 2) {
            const uint32_t d0 = sub2(xr[j][0], pp[0]), d1 = sub2(xr[j][1], pp[1]), d2 = sub2(xr[j + 1][0], pp[0]), d3 = sub2(xr[j + 1][1], pp[1]);
            mma_bf16(s[0], xr[j][0], xr[j][1], xr[j + 1][0], xr[j + 1][1], 0x3f803f80u, 0x3f803f80u);
            mma_bf16(s[1], d0, d1, d2, d3, d0, d2);
            mma_bf16(s[2], d0, d1, d2, d3, d1, d3);
        }
        if (t == (g >> 1)) {
            float2* rp = rsum + ri;
            asm volatile("red.relaxed.gpu.global.add.v2.f32 [%0], {%1, %2};" ::"l"(rp), "f"(fmaf(-80.f, p0, s[0][0])), "f"((g & 1) ? s[1][1] : s[1][0]) : "memory");
            asm volatile("red.relaxed.gpu.global.add.v2.f32 [%0], {%1, %2};" ::"l"(rp + 4), "f"(fmaf(-80.f, p1, s[0][2])), "f"((g & 1) ? s[2][3] : s[2][2]) : "memory");
        }
        asm volatile("cp.async.bulk.wait_group.read 0;" ::: "memory");
        TSTAMP2(6);
        if (tid == 0) DBGC(63);
        if (tid == 128) DBGC(28);
        if (tid == 0) DBGCAL(2);
        GSTAMP(g_tim1, 14);
        SPAN(1 + 4 * layer, 3);
    }
}

static int h_nsm;
static void* h_sym[11];
static TileTab h_tab;
static CUtensorMap h_tmX0, h_tmX1, h_tmR0, h_tmR1, h_tmX1st, h_tmOut, h_tmWq, h_tmWo, h_tmWt;
typedef CUresult (*PFN_encodeTiled)(CUtensorMap*, CUtensorMapDataType, cuuint32_t, void*, const cuuint64_t*, const cuuint64_t*,
                                    const cuuint32_t*, const cuuint32_t*, CUtensorMapInterleave, CUtensorMapSwizzle,
                                    CUtensorMapL2promotion, CUtensorMapFloatOOBfill);
static void make_tmap(CUtensorMap* tm, const void* ptr, uint64_t cols, uint64_t rows, uint32_t bc, uint32_t br, CUtensorMapSwizzle sw, uint64_t pitch = 0, uint64_t hi = 0, uint32_t bh = 2) {
    static PFN_encodeTiled fn = nullptr;
    if (!fn) {
        void* p = nullptr; cudaDriverEntryPointQueryResult qr;
        cudaGetDriverEntryPoint("cuTensorMapEncodeTiled", &p, cudaEnableDefault, &qr);
        fn = (PFN_encodeTiled)p;
    }
    if (br == 0) {
        cuuint64_t dims[5] = {16, 2, rows / 8, 4, cols / 16}; cuuint64_t strides[4] = {cols * 2, cols * 16, cols * 4, 32};
        cuuint32_t box[5] = {16, 2, bc, 4, 5}; cuuint32_t es[5] = {1, 1, 1, 1, 1};
        fn(tm, CU_TENSOR_MAP_DATA_TYPE_BFLOAT16, 5, const_cast<void*>(ptr), dims, strides, box, es, CU_TENSOR_MAP_INTERLEAVE_NONE, sw,
           CU_TENSOR_MAP_L2_PROMOTION_L2_128B, CU_TENSOR_MAP_FLOAT_OOB_FILL_NONE);
        return;
    }
    if (bh == 0) {
        cuuint64_t dims[5] = {64, 64, 2, 16, 10}; cuuint64_t strides[4] = {pitch * 2, hi * 2, cols * 2, rows * 2};
        cuuint32_t box[5] = {64, 64, 2, 1, 1}; cuuint32_t es[5] = {1, 1, 1, 1, 1};
        fn(tm, CU_TENSOR_MAP_DATA_TYPE_BFLOAT16, 5, const_cast<void*>(ptr), dims, strides, box, es, CU_TENSOR_MAP_INTERLEAVE_NONE, sw,
           CU_TENSOR_MAP_L2_PROMOTION_L2_128B, CU_TENSOR_MAP_FLOAT_OOB_FILL_NONE);
        return;
    }
    if (hi) {
        cuuint64_t dims[3] = {cols, rows, hi == 64 ? 32u : hi == 16 ? 120u : 2u}; cuuint64_t strides[2] = {pitch * 2, hi * 2};
        cuuint32_t box[3] = {bc, br, bh}; cuuint32_t es[3] = {1, 1, 1};
        fn(tm, CU_TENSOR_MAP_DATA_TYPE_BFLOAT16, 3, const_cast<void*>(ptr), dims, strides, box, es, CU_TENSOR_MAP_INTERLEAVE_NONE, sw,
           CU_TENSOR_MAP_L2_PROMOTION_L2_128B, CU_TENSOR_MAP_FLOAT_OOB_FILL_NONE);
        return;
    }
    cuuint64_t dims[2] = {cols, rows}; cuuint64_t strides[1] = {(pitch ? pitch : cols) * 2};
    cuuint32_t box[2] = {bc, br}; cuuint32_t es[2] = {1, 1};
    fn(tm, CU_TENSOR_MAP_DATA_TYPE_BFLOAT16, 2, const_cast<void*>(ptr), dims, strides, box, es, CU_TENSOR_MAP_INTERLEAVE_NONE, sw,
       CU_TENSOR_MAP_L2_PROMOTION_L2_128B, CU_TENSOR_MAP_FLOAT_OOB_FILL_NONE);
}
template <typename... Args>
static void launch_pdl(void (*kern)(Args...), int grid, int block, int smem, Args... args) {
    cudaLaunchConfig_t cfg = {};
    cfg.gridDim = dim3(grid); cfg.blockDim = dim3(block); cfg.dynamicSmemBytes = smem; cfg.stream = cudaStreamPerThread;
    cudaLaunchAttribute at[1];
    at[0].id = cudaLaunchAttributeProgrammaticStreamSerialization; at[0].val.programmaticStreamSerializationAllowed = 1;
    cfg.attrs = at; cfg.numAttrs = 1;
    cudaLaunchKernelEx(&cfg, kern, args...);
}
static void launch_stage(int k, void* const* d_in, void* d_out) {
    const KgIn kg = {(const bf16*)d_in[4], (const bf16*)d_in[5], (const bf16*)d_in[6], (const bf16*)d_in[7], (const bf16*)d_in[8], (const bf16*)d_in[9], (const bf16*)d_in[0], (const bf16*)d_in[1], (const bf16*)d_in[2],
                      (uint4*)h_sym[0], (uint4*)h_sym[1], (uint4*)h_sym[2], (uint4*)h_sym[3], (uint4*)h_sym[4], (float*)h_sym[5]};
    switch (k) {
        case 0: kgen_kernel<<<128, 512, KG_SMEM, cudaStreamPerThread>>>(kg, h_tmWq, h_tmWo, h_tmWt); break;
        case 1: launch_pdl(a1_kernel, h_nsm, A1_THREADS, A1_SMEM, 0, (const bf16*)d_in[0], (const unsigned char*)h_sym[1], (const unsigned char*)h_sym[2], (float2*)h_sym[4], (uint4*)h_sym[6], h_tmX0, h_tmR0, h_tmX1st, h_tab); break;
        case 3: launch_pdl(conv_kernel, DM / CV_CPB, CV_THREADS, CV_SMEM, 0, (const uint4*)h_sym[7], (const float4*)h_sym[4], (const bf16*)h_sym[8], (bf16*)h_sym[9], (const uint4*)h_sym[0], h_tmOut); break;
        case 5: launch_pdl(a1_kernel, h_nsm, A1_THREADS, A1_SMEM, 1, (const bf16*)d_in[0], (const unsigned char*)h_sym[1], (const unsigned char*)h_sym[2], (float2*)h_sym[4], (uint4*)h_sym[6], h_tmX1, h_tmR1, h_tmX1st, h_tab); break;
        case 7: launch_pdl(conv_kernel, DM / CV_CPB, CV_THREADS, CV_SMEM, 1, (const uint4*)h_sym[7] + SEQ / 8, (const float4*)h_sym[4] + SEQ / 2, (const bf16*)h_sym[8], (bf16*)h_sym[10], (const uint4*)h_sym[0], h_tmOut); break;
        default: break;
    }
}
static int n_stage_kernels() { return 9; }
static const char* stage_name(int k) { const char* n[] = {"kgen", "a1", "a2", "conv", "tr", "a1", "a2", "conv", "tr"}; return n[k]; }

extern "C" void kernel_launch(void* const* d_in, const int* in_sizes, int n_in, void* d_out, int out_size) {
    (void)in_sizes; (void)n_in; (void)out_size;
    static const void *p_in = nullptr, *p_w1 = nullptr, *p_w2 = nullptr, *p_out = nullptr;
    if (p_in != d_in[0] || p_w1 != d_in[1] || p_w2 != d_in[2] || p_out != d_out) {
        cudaFuncSetAttribute(conv_kernel, cudaFuncAttributeMaxDynamicSharedMemorySize, CV_SMEM);
        cudaFuncSetAttribute(kgen_kernel, cudaFuncAttributeMaxDynamicSharedMemorySize, KG_SMEM);
        cudaFuncSetAttribute(a1_kernel, cudaFuncAttributeMaxDynamicSharedMemorySize, A1_SMEM);
        int dev; cudaGetDevice(&dev); cudaDeviceGetAttribute(&h_nsm, cudaDevAttrMultiProcessorCount, dev);
        if (h_nsm != 132) h_nsm = 128;
        h_tab.ns = h_nsm == 132 ? 132 : ~0u;
        for (int i = 0; i < 264; i++) {
            const int h = (i - 64) >> 1;
            const int t = i >= 132 ? i - 132 : i < 64 ? ((i >> 1) & 7) * 16 + (i >> 4) * 2 + (i & 1) : i < 120 ? (1 + h % 7) * 16 + 8 + (h / 7) * 2 + (i & 1) : i < 124 ? 128 : i - 116;
            const int hg = (4 * (t >> 6) + (t & 3)) & 7;
            h_tab.e[i] = {(unsigned char)((t >> 2) & 15), (unsigned char)hg, (unsigned char)(5 * (hg >> 2)), (unsigned char)t, (uint32_t)(hg * 10 * WQ_STAGE)};
        }
        cudaGetSymbolAddress(&h_sym[0], g_tap); cudaGetSymbolAddress(&h_sym[1], g_wq); cudaGetSymbolAddress(&h_sym[2], g_wo);
        cudaGetSymbolAddress(&h_sym[3], g_halo); cudaGetSymbolAddress(&h_sym[4], g_sum); cudaGetSymbolAddress(&h_sym[5], g_csp); cudaGetSymbolAddress(&h_sym[6], g_of);
        cudaGetSymbolAddress(&h_sym[7], g_piv); cudaGetSymbolAddress(&h_sym[8], g_x1T); cudaGetSymbolAddress(&h_sym[9], g_xcT); cudaGetSymbolAddress(&h_sym[10], g_yT);
        void *px1, *px2;
        cudaGetSymbolAddress(&px1, g_x1T); cudaGetSymbolAddress(&px2, g_xcT);
        make_tmap(&h_tmX0, d_in[0], 128 * 640, 64, 64, 64, CU_TENSOR_MAP_SWIZZLE_128B, 1280, 640, 0);
        make_tmap(&h_tmX1, px2, 128, 64 * XCP, 64, 64, CU_TENSOR_MAP_SWIZZLE_128B, XCP, 64, 0);
        make_tmap(&h_tmR0, d_in[0], 640, 1024, 80, 64, CU_TENSOR_MAP_SWIZZLE_NONE, 1280, 640, 1);
        make_tmap(&h_tmR1, px2, 64, 640, 64, 80, CU_TENSOR_MAP_SWIZZLE_128B, XCP, 64, 1);
        make_tmap(&h_tmX1st, px1, 2048, 640, 64, 80, CU_TENSOR_MAP_SWIZZLE_128B, XCP);
        make_tmap(&h_tmWq, d_in[1], 16, 640, 16, 32, CU_TENSOR_MAP_SWIZZLE_32B, 1920, 16, 5);
        make_tmap(&h_tmWo, d_in[2], 640, 640, 4, 0, CU_TENSOR_MAP_SWIZZLE_32B);
        make_tmap(&h_tmWt, d_in[2], 640, 640, 2, 0, CU_TENSOR_MAP_SWIZZLE_32B);
        make_tmap(&h_tmOut, d_out, 640, 1024, 80, 8, CU_TENSOR_MAP_SWIZZLE_NONE, 1280, 640, 1);
        p_in = d_in[0]; p_w1 = d_in[1]; p_w2 = d_in[2]; p_out = d_out;
    }
    for (int k = 0; k < n_stage_kernels(); k++) launch_stage(k, d_in, d_out);
}
```

```cpp
#include <cuda_runtime.h>
#include <cuda_bf16.h>
#include <stdint.h>
#include <cuda.h>

typedef __nv_bfloat16 bf16;

constexpr int SEQ = 2048;
constexpr int DM = 640;
constexpr int NMODE = 192;

__device__ __forceinline__ float bf2f(bf16 v) { return __bfloat162float(v); }
__device__ __forceinline__ float rbf(float v) {
    uint32_t r;
    asm("cvt.rn.bf16x2.f32 %0, %1, %2;" : "=r"(r) : "f"(v), "f"(0.f));
    return __uint_as_float(r);
}
__device__ __forceinline__ uint32_t pack2(float lo, float hi) {
    __nv_bfloat162 t = __floats2bfloat162_rn(lo, hi);
    return *reinterpret_cast<uint32_t*>(&t);
}
__device__ __forceinline__ void pdl_sync() {
    asm volatile("griddepcontrol.wait;" ::: "memory");
    asm volatile("griddepcontrol.launch_dependents;" ::: "memory");
}
__device__ __forceinline__ float sqrt_apx(float v) { float r; asm("sqrt.approx.ftz.f32 %0, %1;" : "=f"(r) : "f"(v)); return r; }
__device__ __forceinline__ float rcp_apx(float v) { float r; asm("rcp.approx.ftz.f32 %0, %1;" : "=f"(r) : "f"(v)); return r; }
__device__ __forceinline__ uint32_t smem_u32(const void* p) { return (uint32_t)__cvta_generic_to_shared(p); }

constexpr int TAPB = 2 * 152 * 8;
__device__ __align__(128) uint4 g_tap[DM * 128];
#define XPAD 64
constexpr int XCP = SEQ + XPAD;
__device__ __align__(128) bf16 g_x1T[DM * XCP];
__device__ __align__(128) bf16 g_xcT[DM * XCP];
__device__ __align__(128) uint4 g_of[128 * 1280];
constexpr int WQ_STAGE = 240 * 128, WOB = 80 * 160;
__device__ __align__(128) uint4 g_wq[8 * 10 * WQ_STAGE / 16];
__device__ __align__(128) uint4 g_wo[64 * WOB / 16];
__device__ __align__(16) float g_csp[10 * 1920];
#define FSTR 32
__device__ __align__(128) float2 g_sum[2 * SEQ + 256 * FSTR];
__device__ __align__(16) bf16 g_piv[2 * SEQ];
__device__ __align__(128) bf16 g_yT[DM * XCP];
__device__ uint32_t g_epoch;
__device__ __align__(16) unsigned long long g_rstat[SEQ];
__device__ __align__(128) uint4 g_halo[640 * 148];
__device__ __forceinline__ unsigned long long tagw(uint32_t payload, uint32_t tag) { return ((unsigned long long)tag << 32) | payload; }
__device__ __forceinline__ ulonglong2 ld_tag2(const ulonglong2* p) {
    ulonglong2 v;
    asm volatile("ld.relaxed.gpu.global.v2.u64 {%0, %1}, [%2];" : "=l"(v.x), "=l"(v.y) : "l"(p) : "memory");
    return v;
}
__device__ __forceinline__ bool tag_ok(ulonglong2 v, uint32_t tag) { return (uint32_t)(v.x >> 32) == tag && (uint32_t)(v.y >> 32) == tag; }
__device__ __forceinline__ uint32_t ld_epoch() { uint32_t v; asm volatile("ld.relaxed.gpu.global.u32 %0, [%1];" : "=r"(v) : "l"(&g_epoch) : "memory"); return v + 1; }
constexpr int SPIN_MAX = 1 << 20;
__device__ uint32_t g_started[4];
__device__ __forceinline__ void sm_started(int slot) { asm volatile("red.relaxed.gpu.global.add.u32 [%0], 1;" ::"l"(g_started + slot) : "memory"); }
__device__ __noinline__ void sm_idle(int slot) {
    if (threadIdx.x) return;
    sm_started(slot);
    const uint32_t want = ld_epoch() * gridDim.x;
    pdl_sync();
#pragma unroll 1
    for (int it = 0; it < SPIN_MAX; it++) {
        uint32_t v;
        asm volatile("ld.relaxed.gpu.global.u32 %0, [%1];" : "=r"(v) : "l"(g_started + slot) : "memory");
        if ((int)(v - want) >= 0) break;
        __nanosleep(100);
    }
}
struct TileTab { uint32_t ns, pad; struct { unsigned char mb, hg, kb0, tile; uint32_t woff; } __align__(8) e[264]; };
__device__ __forceinline__ bool elect() {
    uint32_t p;
    asm volatile("{\n.reg .pred p;\nelect.sync _|p, 0xffffffff;\nselp.b32 %0, 1, 0, p;\n}" : "=r"(p));
    return p;
}
#define DBG_SYMS
#define TSTAMP(i)
#define TSTAMP1(i)
#define TSTAMP1T(i, t)
#define TSTAMP1X(i, t)
#define SPAN(k, i)
#define GSTAMP(arr, i)
#define TSTAMP2(i)
#define TSTAMP3(i)
#define TSTAMP4(i)
#define TSTAMPK(i, t)
#define TSTAMPC(i)
#define DBGC(i)
#define DBGV(i, v)
#define DBGCAL(i)

#define CSA(i)
#define CSA_END
#define CST(i)
#define CST_END
#define CST_EXTRA 0
__device__ __forceinline__ void mma_bf16(float* d, uint32_t a0, uint32_t a1, uint32_t a2, uint32_t a3, uint32_t b0, uint32_t b1) {
    asm volatile("mma.sync.aligned.m16n8k16.row.col.f32.bf16.bf16.f32 {%0,%1,%2,%3}, {%4,%5,%6,%7}, {%8,%9}, {%0,%1,%2,%3};"
                 : "+f"(d[0]), "+f"(d[1]), "+f"(d[2]), "+f"(d[3]) : "r"(a0), "r"(a1), "r"(a2), "r"(a3), "r"(b0), "r"(b1));
}
__device__ __forceinline__ void mma_bf16_k8(float* d, uint32_t a0, uint32_t a1, uint32_t b0) {
    asm volatile("mma.sync.aligned.m16n8k8.row.col.f32.bf16.bf16.f32 {%0,%1,%2,%3}, {%4,%5}, {%6}, {%0,%1,%2,%3};"
                 : "+f"(d[0]), "+f"(d[1]), "+f"(d[2]), "+f"(d[3]) : "r"(a0), "r"(a1), "r"(b0));
}
__device__ __forceinline__ void ldsm_x4(uint32_t* r, uint32_t addr) {
    asm volatile("ldmatrix.sync.aligned.m8n8.x4.shared.b16 {%0,%1,%2,%3}, [%4];"
                 : "=r"(r[0]), "=r"(r[1]), "=r"(r[2]), "=r"(r[3]) : "r"(addr));
}

__device__ __forceinline__ void ldsm_x4_t(uint32_t* r, uint32_t addr) {
    asm volatile("ldmatrix.sync.aligned.m8n8.x4.trans.shared.b16 {%0,%1,%2,%3}, [%4];"
                 : "=r"(r[0]), "=r"(r[1]), "=r"(r[2]), "=r"(r[3]) : "r"(addr));
}
__device__ __forceinline__ void mbar_init(uint32_t bar, int count) { asm volatile("mbarrier.init.shared::cta.b64 [%0], %1;" ::"r"(bar), "r"(count)); }
__device__ __forceinline__ void mbar_arrive(uint32_t bar) { asm volatile("mbarrier.arrive.shared::cta.b64 _, [%0];" ::"r"(bar) : "memory"); }
__device__ __forceinline__ void mbar_wait(uint32_t bar, uint32_t parity) {
    asm volatile("{\n.reg .pred p;\nWAIT_LOOP:\n"
                 "mbarrier.try_wait.parity.shared::cta.b64 p, [%0], %1;\n"
                 "@p bra.uni WAIT_DONE;\nbra.uni WAIT_LOOP;\nWAIT_DONE:\n}" ::"r"(bar), "r"(parity) : "memory");
}

__device__ __forceinline__ void mbar_expect_tx(uint32_t bar, uint32_t bytes) {
    asm volatile("mbarrier.arrive.expect_tx.shared::cta.b64 _, [%0], %1;" ::"r"(bar), "r"(bytes) : "memory");
}
__device__ __forceinline__ void tma_load_2d(uint32_t dst, const void* tmap, int c0, int c1, uint32_t bar) {
    asm volatile("cp.async.bulk.tensor.2d.shared::cluster.global.mbarrier::complete_tx::bytes [%0], [%1, {%3, %4}], [%2];"
                 ::"r"(dst), "l"(tmap), "r"(bar), "r"(c0), "r"(c1) : "memory");
}
__device__ __forceinline__ void tma_load_3d(uint32_t dst, const void* tmap, int c0, int c1, int c2, uint32_t bar) {
    asm volatile("cp.async.bulk.tensor.3d.shared::cluster.global.mbarrier::complete_tx::bytes [%0], [%1, {%3, %4, %5}], [%2];"
                 ::"r"(dst), "l"(tmap), "r"(bar), "r"(c0), "r"(c1), "r"(c2) : "memory");
}
__device__ __forceinline__ void fence_async_smem() { asm volatile("fence.proxy.async.shared::cta;" ::: "memory"); }
__device__ __forceinline__ void bulk_load(uint32_t dst, const void* src, uint32_t bytes, uint32_t bar) {
    asm volatile("cp.async.bulk.shared::cluster.global.mbarrier::complete_tx::bytes [%0], [%1], %2, [%3];"
                 ::"r"(dst), "l"(src), "r"(bytes), "r"(bar) : "memory");
}
__device__ __forceinline__ void stsm_x4(uint32_t addr, uint32_t r0, uint32_t r1, uint32_t r2, uint32_t r3) {
    asm volatile("stmatrix.sync.aligned.m8n8.x4.shared.b16 [%0], {%1,%2,%3,%4};" ::"r"(addr), "r"(r0), "r"(r1), "r"(r2), "r"(r3) : "memory");
}
__device__ __forceinline__ void stsm_x4_t(uint32_t addr, uint32_t r0, uint32_t r1, uint32_t r2, uint32_t r3) {
    asm volatile("stmatrix.sync.aligned.m8n8.x4.trans.shared.b16 [%0], {%1,%2,%3,%4};" ::"r"(addr), "r"(r0), "r"(r1), "r"(r2), "r"(r3) : "memory");
}
__device__ __forceinline__ void prefetch_tmap(const void* tmap) { asm volatile("prefetch.tensormap [%0];" ::"l"(tmap) : "memory"); }

__device__ __forceinline__ float2 cexp_at(float wr2, float wi, float p) {
    float er;
    asm("ex2.approx.ftz.f32 %0, %1;" : "=f"(er) : "f"(wr2 * p));
    float th = wi * p;
    const float k = rintf(th * 0.15915494309189535f);
    th = fmaf(k, -6.2831854820251465f, th);
    th = fmaf(k, 1.7484555314695172e-7f, th);
    return make_float2(er * __cosf(th), er * __sinf(th));
}
__device__ __forceinline__ float2 cmul(float2 a, float2 b) {
    return make_float2(fmaf(a.x, b.x, -a.y * b.y), fmaf(a.x, b.y, a.y * b.x));
}
__device__ __forceinline__ float2 csqr(float2 a) { return make_float2(fmaf(a.x, a.x, -a.y * a.y), (a.x + a.x) * a.y); }
__device__ __forceinline__ uint32_t packh(float2 v) {
    uint32_t r;
    asm("cvt.rn.f16x2.f32 %0, %1, %2;" : "=r"(r) : "f"(v.y), "f"(v.x));
    return r;
}
__device__ __forceinline__ void mma_f16(float* d, uint32_t a0, uint32_t a1, uint32_t a2, uint32_t a3, uint32_t b0, uint32_t b1) {
    asm volatile("mma.sync.aligned.m16n8k16.row.col.f32.f16.f16.f32 {%0,%1,%2,%3}, {%4,%5,%6,%7}, {%8,%9}, {%0,%1,%2,%3};"
                 : "+f"(d[0]), "+f"(d[1]), "+f"(d[2]), "+f"(d[3]) : "r"(a0), "r"(a1), "r"(a2), "r"(a3), "r"(b0), "r"(b1));
}

struct KgIn { const bf16 *logA, *Aim, *Cre, *Cim, *logdt, *dsk, *x, *wqkv, *wo; uint4 *tap, *wq, *wop, *halo, *sum; float* csp; };
constexpr int KG_THREADS = NMODE / 2;

constexpr int KG_BUF = 15 * 12288, KG_BAR = KG_BUF + 6 * 5120, KG_SMEM = KG_BAR + 64;
__global__ void __launch_bounds__(512, 1) kgen_kernel(const KgIn in, const __grid_constant__ CUtensorMap tmWq, const __grid_constant__ CUtensorMap tmWo,
                                                        const __grid_constant__ CUtensorMap tmWt) {
    extern __shared__ __align__(1024) uint4 tabs[];
#define KG_ROT 0
    const int lane = threadIdx.x & 31, w16 = (__shfl_sync(~0u, threadIdx.x >> 5, 0) + KG_ROT) & 15, grp = w16 / 3, warp = w16 - 3 * grp;
    const int d = blockIdx.x * 5 + grp, tid = warp * 32 + lane;
    uint4* tab = tabs + grp * (3 * 768);
    SPAN(0, 0); SPAN(0, 1);
    TSTAMPK(0, 0);
    asm volatile("griddepcontrol.launch_dependents;" ::: "memory");
    if (w16 == 15) {
        const uint32_t b0 = smem_u32(tab), wbar = b0 + 6 * 5120;
        const int blk = blockIdx.x, nq = blk < 112 ? 4 : 2, nj = nq + (blk < 64 ? 1 : 2);
        auto fetch = [&](int i) {
            const uint32_t dst = b0 + i * 5120, bar = wbar + 8 * i;
            if (i < nq) {
                const int p = blk + 64 * (i & 2), kb = p / 24;
                mbar_expect_tx(bar, 5120);
                tma_load_3d(dst, &tmWq, 0, kb * 64 + (i & 1) * 32, (p - 24 * kb) * 5, bar);
            } else if (i < nj) {
                const int o = i == nq ? blk : 255 - blk;
                mbar_expect_tx(bar, o < 128 ? 5120 : 2560);
                asm volatile("cp.async.bulk.tensor.5d.shared::cluster.global.mbarrier::complete_tx::bytes [%0], [%1, {%3, %3, %4, %3, %5}], [%2];"
                             ::"r"(dst), "l"(o < 128 ? &tmWo : &tmWt), "r"(bar), "r"(0), "r"((o & 7) * 10 + (o >> 6) * 4), "r"(((o >> 3) & 7) * 5) : "memory");
            }
        };
        const bool one = elect();
        if (one) {
#pragma unroll
            for (int i = 0; i < 6; i++) mbar_init(wbar + 8 * i, 1);
            asm volatile("fence.mbarrier_init.release.cluster;" ::: "memory");
#pragma unroll
            for (int i = 0; i < 6; i++) fetch(i);
        }
        __syncwarp();
#pragma unroll
        for (int i = 1; i <= 5; i++) asm volatile("bar.arrive %0, 128;" ::"r"(i) : "memory");
        if (one) {
#pragma unroll 1
            for (int i = 0; i < nj; i++) {
                const int p = blk + 64 * (i & 2), kb = p / 24, hg = p & 7, sec = (p - 24 * kb) >> 3, o = i == nq ? blk : 255 - blk, cg = (o >> 3) & 7, hb = o & 7;
                const unsigned char* dst = i < nq ? reinterpret_cast<unsigned char*>(in.wq) + (hg * 10 + (hg < 4 ? kb : kb < 5 ? kb + 5 : kb - 5)) * WQ_STAGE + ((i & 1) * 3 + sec) * 5120
                                                  : reinterpret_cast<unsigned char*>(in.wop) + (cg * 8 + (hb == cg ? 0 : hb + (hb < cg))) * WOB + (o >> 6) * 5120;
                mbar_wait(wbar + 8 * i, 0);
                if (i == 0) TSTAMPK(2, (15 - KG_ROT) * 32);
                if (i == 3) TSTAMPK(5, (15 - KG_ROT) * 32);
                asm volatile("cp.async.bulk.global.shared::cta.bulk_group [%0], [%1], %2;" ::"l"(dst), "r"(b0 + i * 5120), "r"(i < nq || o < 128 ? 5120 : 2560) : "memory");
            }
            asm volatile("cp.async.bulk.commit_group;" ::: "memory");
            asm volatile("cp.async.bulk.wait_group.read 0;" ::: "memory");
        }
        TSTAMPK(11, (15 - KG_ROT) * 32);
        return;
    }
    const bf16 pdt = in.logdt[d], pdsk = in.dsk[d];
    const uint32_t pla = reinterpret_cast<const uint32_t*>(in.logA)[d * KG_THREADS + tid], pai = reinterpret_cast<const uint32_t*>(in.Aim)[d * KG_THREADS + tid];
    const uint32_t pcr = reinterpret_cast<const uint32_t*>(in.Cre)[d * KG_THREADS + tid], pci = reinterpret_cast<const uint32_t*>(in.Cim)[d * KG_THREADS + tid];
    const bf16* pfq = tid < 30 ? in.wqkv + (size_t)(d * 30 + tid) * 64 : tid < 40 ? in.wo + (size_t)(d * 10 + tid - 30) * 64 : in.x + (size_t)(d * 32 + tid - 40) * 64;
#define KG_PF 0
    if (tid < (KG_PF == 3 ? 0 : KG_PF ? 40 : 72)) asm volatile("prefetch.global.L2 [%0];" ::"l"(pfq));
    asm volatile("st.global.v4.u32 [%0], {%1,%1,%1,%1};" ::"l"(in.halo + d * 148 + tid), "r"(~0u));
    if (tid < 52) asm volatile("st.global.v4.u32 [%0], {%1,%1,%1,%1};" ::"l"(in.halo + d * 148 + 96 + tid), "r"(~0u));
    else if (w16 == 2) {
        if (lane < 16) in.sum[blockIdx.x * 16 + lane] = make_uint4(0, 0, 0, 0);
        else if (lane < 20) reinterpret_cast<uint32_t*>(in.sum + 2048)[(blockIdx.x * 4 + lane - 16) * FSTR] = 0;
    }
    const uint32_t tw = smem_u32(tab) + warp * 12288;
    const int g = lane >> 2, t = lane & 3;
    const uint32_t sta = tw + lane * 128 + ((2 * (lane & 3) + ((lane >> 2) & 1)) << 4);
    const uint32_t lda = tw + t * 128 + ((g ^ (2 * t)) << 4);
    const uint32_t stb = tw + lane * 8, ldb = tw + g * 512 + (g & 3) * 32 + t * 8;
    auto sts4 = [&](int e, int off, uint32_t a, uint32_t b, uint32_t c, uint32_t dd) {
        asm volatile("st.shared.v4.u32 [%0], {%1,%2,%3,%4};" ::"r"((sta ^ (e << 4)) + off), "r"(a), "r"(b), "r"(c), "r"(dd) : "memory");
    };
    auto lds4 = [&](int sp, int off, uint32_t* r) {
        asm volatile("ld.shared.v4.u32 {%0,%1,%2,%3}, [%4];" : "=r"(r[0]), "=r"(r[1]), "=r"(r[2]), "=r"(r[3]) : "r"((lda ^ ((sp & 1) << 4)) + sp * 512 + off) : "memory");
    };
    const float dt = rbf(expf(bf2f(pdt)));
    float2 C[2], y1[2], z8[2], y128[2];
    float cmax = 0.f;
#pragma unroll
    for (int m = 0; m < 2; m++) {
        const float wr2 = -rbf(expf(__uint_as_float(m ? pla & 0xffff0000u : pla << 16))) * dt * 1.4426950408889634f;
        const float wi = __uint_as_float(m ? pai & 0xffff0000u : pai << 16) * dt;
        C[m] = make_float2(__uint_as_float(m ? pcr & 0xffff0000u : pcr << 16) * dt, -__uint_as_float(m ? pci & 0xffff0000u : pci << 16) * dt);
        cmax = fmaxf(cmax, fmaxf(fabsf(C[m].x), fabsf(C[m].y)));
        y1[m] = cexp_at(wr2, -wi, 1.f); z8[m] = cexp_at(wr2, wi, 8.f); y128[m] = cexp_at(wr2, -wi, 128.f);
    }
    const int ex = min(max((int)(__reduce_max_sync(~0u, __float_as_uint(cmax)) >> 23), 20), 240);
    const float scale = __uint_as_float((uint32_t)(127 + 10 + 127 - ex) << 23), unscale = 2.0f * __uint_as_float((uint32_t)(ex - 10) << 23);
    TSTAMPK(4, 64);
    if (KG_PF >= 2 && tid >= 40 && tid < 72) asm volatile("prefetch.global.L2 [%0];" ::"l"(pfq));
    float k2048 = 0.f;
    float acc[5][4];
#pragma unroll
    for (int j = 0; j < 5; j++)
#pragma unroll
        for (int k = 0; k < 4; k++) acc[j][k] = 0.f;
    uint32_t af[8][4];
    {
        float2 h0[2], h1[2], g0[2], g1[2], g2[2], g2b[2], g3[2], g4[2], y2[2], y4[2];
#pragma unroll
        for (int m = 0; m < 2; m++) {
            h0[m] = make_float2(1.f, 0.f); h1[m] = csqr(csqr(csqr(z8[m])));
            g0[m] = make_float2(C[m].x * scale, C[m].y * scale);
            g1[m] = cmul(g0[m], y128[m]);
            const float2 y256 = csqr(y128[m]), y512 = csqr(y256);
            g2b[m] = g2[m] = cmul(g0[m], y256); g3[m] = cmul(g0[m], y512); g4[m] = cmul(g3[m], y512);
            y2[m] = csqr(y1[m]); y4[m] = csqr(y2[m]);
            const float2 y1024 = csqr(y512);
            k2048 += fmaf(g4[m].x, y1024.x, -g4[m].y * y1024.y);
        }
#pragma unroll
        for (int e = 0; e < 8; e++) {
            sts4(e, 0, packh(h0[0]), packh(h1[0]), packh(h0[1]), packh(h1[1]));
            sts4(e, 4096, packh(g0[0]), packh(g0[1]), packh(g1[0]), packh(g1[1]));
#pragma unroll
            for (int m = 0; m < 2; m++)
                if (e < 7) { h0[m] = e ? cmul(h0[m], z8[m]) : z8[m]; h1[m] = cmul(h1[m], z8[m]); g0[m] = cmul(g0[m], y1[m]); g1[m] = cmul(g1[m], y1[m]); }
            if (e < 5) k2048 += __shfl_xor_sync(~0u, k2048, 1 << e);
        }
        if (KG_PF == 1 && tid >= 40 && tid < 72) asm volatile("prefetch.global.L2 [%0];" ::"l"(pfq));
        __syncwarp();
#pragma unroll
        for (int e = 0; e < 8; e++) {
            uint32_t b[4];
            lds4(e, 0, af[e]); lds4(e, 4096, b);
            sts4(e, 8192, packh(g2[0]), packh(g2[1]), packh((e & 1) ? cmul(g3[0], y4[0]) : g3[0]), packh((e & 1) ? cmul(g3[1], y4[1]) : g3[1]));
            asm volatile("st.shared.v2.u32 [%0], {%1,%2};" ::"r"((stb ^ ((e & 3) << 5)) + e * 512), "r"(packh(g4[0])), "r"(packh(g4[1])) : "memory");
#pragma unroll
            for (int m = 0; m < 2; m++)
                if (e < 7) {
                    g2[m] = e == 3 ? cmul(g2b[m], y128[m]) : cmul(g2[m], y2[m]);
                    if (e & 1) g3[m] = cmul(g3[m], y128[m]);
                    g4[m] = cmul(g4[m], y128[m]);
                }
            mma_f16(acc[0], af[e][0], af[e][1], af[e][2], af[e][3], b[0], b[1]);
            mma_f16(acc[1], af[e][0], af[e][1], af[e][2], af[e][3], b[2], b[3]);
        }
    }
    TSTAMPK(6, 64);
    __syncwarp();
#pragma unroll
    for (int sp = 0; sp < 8; sp++) {
        uint32_t c[4], e0, e1;
        lds4(sp, 8192, c);
        asm volatile("ld.shared.v2.u32 {%0,%1}, [%2];" : "=r"(e0), "=r"(e1) : "r"(ldb ^ (sp << 5)) : "memory");
        mma_f16(acc[2], af[sp][0], af[sp][1], af[sp][2], af[sp][3], c[0], c[1]);
        mma_f16(acc[3], af[sp][0], af[sp][1], af[sp][2], af[sp][3], c[2], c[3]);
        mma_f16(acc[4], af[sp][0], af[sp][1], af[sp][2], af[sp][3], e0, e1);
    }
    {
        float* Pp = reinterpret_cast<float*>(tab + warp * 768);
        auto sw = [](int i) { return i ^ ((i >> 2) & 24); };
#pragma unroll
        for (int h = 0; h < 2; h++) {
            const int b = g + 8 * h;
            *reinterpret_cast<float2*>(Pp + sw(8 * b + 2 * t)) = make_float2(acc[0][2 * h] * unscale, acc[0][2 * h + 1] * unscale);
            *reinterpret_cast<float2*>(Pp + 128 + sw(8 * b + 2 * t)) = make_float2(acc[1][2 * h] * unscale, acc[1][2 * h + 1] * unscale);
            *reinterpret_cast<float2*>(Pp + 256 + sw(4 * b + 2 * (t & 1) + 64 * (t >> 1))) = make_float2(acc[2][2 * h] * unscale, acc[2][2 * h + 1] * unscale);
            *reinterpret_cast<float2*>(Pp + 384 + sw(2 * b + 32 * t)) = make_float2(acc[3][2 * h] * unscale, acc[3][2 * h + 1] * unscale);
            Pp[512 + sw(b + 32 * t)] = acc[4][2 * h] * unscale;
            Pp[512 + sw(b + 32 * t + 16)] = acc[4][2 * h + 1] * unscale;
        }
        if (lane == 0) Pp[640] = k2048 * unscale;
    }
    TSTAMPK(7, 64);
    asm volatile("bar.sync %0, 128;" ::"r"(grp + 1) : "memory");
    TSTAMPK(9, 64);
    const float* Kp = reinterpret_cast<const float*>(tab);
    auto ksum = [&](int i) -> float { return (Kp[i] + Kp[3072 + i]) + Kp[6144 + i]; };
    auto ksum4 = [&](int q) -> float4 {
        q ^= (q >> 2) & 6;
        const float4 a = reinterpret_cast<const float4*>(Kp)[q], b = reinterpret_cast<const float4*>(Kp)[768 + q], c = reinterpret_cast<const float4*>(Kp)[1536 + q];
        return make_float4((a.x + b.x) + c.x, (a.y + b.y) + c.y, (a.z + b.z) + c.z, (a.w + b.w) + c.w);
    };
    {
        uint2* E4 = reinterpret_cast<uint2*>(in.tap + d * 128);
        float4 v = ksum4(tid), u = ksum4(96 + min(tid, 64));
        const float cor = rbf(ksum(tid == 95 ? 384 : 512));
        if (tid == 0) v.x += bf2f(pdsk);
        if (tid == 95) v.w -= cor;
        if (tid == 31) u.w -= cor;
        const uint32_t lo = pack2(v.x, v.y), hi = pack2(v.z, v.w);
        if (tid < 64) {
            E4[6 + tid] = make_uint2(lo, hi);
            E4[(tid < 32 ? 159 : 209 - 32) + tid] = make_uint2(pack2(u.x, u.y), pack2(u.z, u.w));
        } else {
            const uint32_t nx = __shfl_down_sync(~0u, lo, 1);
            in.tap[d * 128 + 35 + tid - 64] = make_uint4(__byte_perm(lo, 0, 0x1010), __byte_perm(lo, hi, 0x5432), __byte_perm(hi, 0, 0x1010), __byte_perm(hi, tid == 95 ? 0u : nx, 0x5432));
            if (tid == 64) E4[241] = make_uint2(pack2(u.x, 0.f), 0u);
        }
    }
    TSTAMPK(10, 64);
    if (warp < (blockIdx.x < 112 ? 2 : 1)) {
        const uint32_t sb = smem_u32(tabs);
        mbar_wait(sb + KG_BAR + 16 * warp, 0); mbar_wait(sb + KG_BAR + 16 * warp + 8, 0);
        uint32_t w[4][4];
        float cs[4] = {0.f, 0.f, 0.f, 0.f};
#pragma unroll
        for (int a = 0; a < 4; a++)
            ldsm_x4_t(w[a], sb + KG_BUF + warp * 10240 + grp * 1024 + ((lane >> 4) * 8 + (lane & 7)) * 32 + ((((lane >> 3) ^ (lane >> 2)) & 1) << 4) + (a >> 1) * 5120 + (a & 1) * 512);
#pragma unroll
        for (int a = 0; a < 4; a++) mma_bf16(cs, w[a][0], w[a][1], w[a][2], w[a][3], 0x3f803f80u, 0x3f803f80u);
        if (t < 2) in.csp[(blockIdx.x + 128 * warp) * 80 + grp * 16 + g + 8 * t] = t ? cs[2] : cs[0];
    }
    SPAN(0, 3);
}

#define CV_SLEEP 40
#define CV_D2 3
#define CV_PDH 12
#define CV_PDF 4
#define CV_HAND 7
constexpr int CV_CPB = 5;
constexpr int CV_THREADS = 512;
constexpr int UPADF = 128;
constexpr int ULEN = UPADF + SEQ;
constexpr int XLEN = SEQ + 16;
constexpr int BX_5 = 0, BX_3 = 3264, BX_9 = 6528, BX_7 = 8960, BX_LEN = 11392;
constexpr int CV_SM_U = 0;
constexpr int CV_SM_T = CV_CPB * ULEN * 2;
constexpr int CV_SM_B = CV_SM_T + CV_CPB * TAPB;
constexpr int CV_SM_X = CV_SM_B + CV_CPB * BX_LEN;
constexpr int CV_SM_Y = (CV_SM_X + CV_CPB * XLEN * 2 + 127) & ~127;
constexpr int CV_SM_CNT = CV_SM_Y + CV_CPB * 8192;
constexpr int CV_SM_O = CV_SM_CNT + 128;
constexpr int CV_SMEM = CV_SM_O + 20480 + CST_EXTRA;
static_assert(ULEN % 128 == 0 && CV_SM_B % 128 == 0 && CV_SM_CNT % 128 == 0, "layout");

__device__ __forceinline__ uint32_t sub2(uint32_t x, uint32_t m) {
    const __nv_bfloat162 d = __hsub2(*reinterpret_cast<const __nv_bfloat162*>(&x), *reinterpret_cast<const __nv_bfloat162*>(&m));
    return *reinterpret_cast<const uint32_t*>(&d);
}
__device__ __forceinline__ uint32_t add2(uint32_t x, uint32_t y) {
    const __nv_bfloat162 d = __hadd2_rn(*reinterpret_cast<const __nv_bfloat162*>(&x), *reinterpret_cast<const __nv_bfloat162*>(&y));
    return *reinterpret_cast<const uint32_t*>(&d);
}
__device__ __forceinline__ void wgmma_fence() { asm volatile("wgmma.fence.sync.aligned;" ::: "memory"); }
__device__ __forceinline__ void wgmma_commit() { asm volatile("wgmma.commit_group.sync.aligned;" ::: "memory"); }
template <int N> __device__ __forceinline__ void wgmma_wait() { asm volatile("wgmma.wait_group.sync.aligned %0;" ::"n"(N) : "memory"); }
__device__ __forceinline__ uint64_t make_desc(uint32_t addr, uint32_t lbo, uint32_t sbo, uint32_t mode) {
    return (uint64_t)((addr & 0x3FFFF) >> 4) | ((uint64_t)(lbo >> 4) << 16) | ((uint64_t)(sbo >> 4) << 32) | ((uint64_t)mode << 62);
}
__device__ __forceinline__ void wgmma_rs128(float (&d)[64], uint2 hi, uint2 lo, uint64_t db, int acc) {
    asm volatile("{\n.reg .pred p;\nsetp.ne.b32 p, %69, 0;\nwgmma.mma_async.sync.aligned.m64n128k16.f32.bf16.bf16 {%0,%1,%2,%3,%4,%5,%6,%7,%8,%9,%10,%11,%12,%13,%14,%15,%16,%17,%18,%19,%20,%21,%22,%23,%24,%25,%26,%27,%28,%29,%30,%31,%32,%33,%34,%35,%36,%37,%38,%39,%40,%41,%42,%43,%44,%45,%46,%47,%48,%49,%50,%51,%52,%53,%54,%55,%56,%57,%58,%59,%60,%61,%62,%63}, {%64,%65,%66,%67}, %68, p, 1, 1, 0;\n}"
                 : "+f"(d[0]), "+f"(d[1]), "+f"(d[2]), "+f"(d[3]), "+f"(d[4]), "+f"(d[5]), "+f"(d[6]), "+f"(d[7]), "+f"(d[8]), "+f"(d[9]), "+f"(d[10]), "+f"(d[11]), "+f"(d[12]), "+f"(d[13]), "+f"(d[14]), "+f"(d[15]), "+f"(d[16]), "+f"(d[17]), "+f"(d[18]), "+f"(d[19]), "+f"(d[20]), "+f"(d[21]), "+f"(d[22]), "+f"(d[23]), "+f"(d[24]), "+f"(d[25]), "+f"(d[26]), "+f"(d[27]), "+f"(d[28]), "+f"(d[29]), "+f"(d[30]), "+f"(d[31]), "+f"(d[32]), "+f"(d[33]), "+f"(d[34]), "+f"(d[35]), "+f"(d[36]), "+f"(d[37]), "+f"(d[38]), "+f"(d[39]), "+f"(d[40]), "+f"(d[41]), "+f"(d[42]), "+f"(d[43]), "+f"(d[44]), "+f"(d[45]), "+f"(d[46]), "+f"(d[47]), "+f"(d[48]), "+f"(d[49]), "+f"(d[50]), "+f"(d[51]), "+f"(d[52]), "+f"(d[53]), "+f"(d[54]), "+f"(d[55]), "+f"(d[56]), "+f"(d[57]), "+f"(d[58]), "+f"(d[59]), "+f"(d[60]), "+f"(d[61]), "+f"(d[62]), "+f"(d[63])
                 : "r"(hi.x), "r"(hi.y), "r"(lo.x), "r"(lo.y), "l"(db), "r"(acc));
}
template <int V> struct Int { __device__ constexpr operator int() const { return V; } };
__device__ __forceinline__ void sts4(uint32_t a, const uint32_t* v) { asm volatile("st.shared.v4.u32 [%0], {%1,%2,%3,%4};" ::"r"(a), "r"(v[0]), "r"(v[1]), "r"(v[2]), "r"(v[3]) : "memory"); }
__device__ __forceinline__ uint32_t lds1(uint32_t a) { uint32_t v; asm volatile("ld.shared.u32 %0, [%1];" : "=r"(v) : "r"(a) : "memory"); return v; }
__device__ __forceinline__ uint4 lds4(uint32_t a) { uint4 v; asm volatile("ld.shared.v4.u32 {%0,%1,%2,%3}, [%4];" : "=r"(v.x), "=r"(v.y), "=r"(v.z), "=r"(v.w) : "r"(a) : "memory"); return v; }
__device__ __forceinline__ void cv_store(unsigned char* p, uint4 x, uint4 y) {
    asm volatile("st.relaxed.gpu.global.v2.u32 [%0], {%1,%2};" ::"l"(p), "r"(add2(x.x, __byte_perm(y.x, y.y, 0x5410))), "r"(add2(x.y, __byte_perm(y.z, y.w, 0x5410))) : "memory");
    asm volatile("st.relaxed.gpu.global.v2.u32 [%0], {%1,%2};" ::"l"(p + 128), "r"(add2(x.z, __byte_perm(y.x, y.y, 0x7632))), "r"(add2(x.w, __byte_perm(y.z, y.w, 0x7632))) : "memory");
}
__device__ __forceinline__ int usw(int ch) { return ch ^ ((ch >> 3) & 1); }
__global__ void __launch_bounds__(CV_THREADS, 1) conv_kernel(int layer, const uint4* __restrict__ piv, const float4* __restrict__ sum, const bf16* __restrict__ x1T,
                                                             bf16* __restrict__ dst, const uint4* __restrict__ tap, const __grid_constant__ CUtensorMap tmOut) {
    extern __shared__ __align__(1024) unsigned char sm[];
    SPAN(3 + 4 * layer, 0);
    bf16* Us = reinterpret_cast<bf16*>(sm + CV_SM_U);
    bf16* Xs = reinterpret_cast<bf16*>(sm + CV_SM_X);
#define CV_IDX int tid; asm volatile("mov.u32 %0, %tid.x;" : "=r"(tid)); const int lane = tid & 31, warp = __shfl_sync(~0u, tid >> 5, 0);
    const int d0 = blockIdx.x * CV_CPB, tile = blockIdx.x; (void)tile;
    const uint32_t cnt = smem_u32(sm + CV_SM_CNT);
    struct Lc { uint32_t a4, a8, uc, ud, y, e4, en, sp, ss; int go; };
    auto lane_consts = [&](int lane, int c) {
        const int mat = lane >> 3, r = lane & 7, g = lane >> 2, ti = lane & 3, e = g - 2 * ti;
        const int j2 = 13 + (r ^ 1) + 8 * (mat >> 1), j3 = j2 + 2, i0 = 8 * (mat & 1);
        const uint32_t sb = smem_u32(sm), oc = sb + usw(16 * (mat >> 1) + 2 * r + (mat & 1)) * 16;
        const Lc l = {sb + CV_SM_B + c * BX_LEN + ((j2 & 1) ? BX_3 + (4 * j2 + i0 + 84) * 2 : BX_5 + (4 * j2 + i0 + 80) * 2),
                      sb + CV_SM_B + c * BX_LEN + ((j3 & 1) ? BX_7 : BX_9) + (8 * j3 + i0 + 136) * 2,
                      oc + CV_SM_U + (c * ULEN + UPADF) * 2, sb + CV_SM_U + (c * ULEN + UPADF) * 2 + usw(16 * mat + 2 * r + 2) * 16, oc + CV_SM_Y + c * 8192,
                      sb + CV_SM_O + 2048 * c + (307 + 2 * g - ti) * 4, sb + CV_SM_T + c * TAPB + (152 + 144 + e) * 8 + 4,
                      e == -5 ? 0x4410u : e == -4 ? 0x1044u : 0x4444u, e == 3 ? 0x4410u : e == 4 ? 0x1044u : 0x4444u,
                      c * XCP * 2 + (lane >> 4) * 256 + (lane & 15) * 8};
        asm volatile("st.shared.u32 [%0], %1;" ::"r"(l.y), "r"(l.a4 ^ l.a8 ^ l.uc ^ l.ud ^ l.e4 ^ l.en ^ l.sp ^ l.ss ^ l.go) : "memory");
        return l;
    };
    unsigned char* const dq = reinterpret_cast<unsigned char*>(dst + (size_t)d0 * XCP);
    auto far = [&](auto T0_, const auto& seq, const Lc& lc, int c, int lane, const uint2 (&f)[20], uint32_t kk) {
        constexpr int T0 = T0_, T1 = T0 + 6, TC = T0 > 7 ? T0 : 7, NS = sizeof(seq) / sizeof(seq[0]), PD = T0 > 7 ? CV_PDH : CV_PDF;
        uint32_t bq[28], yw[4], yz[4], P, S;
        uint4 xv, yv;
        asm("prmt.b32 %0, %1, 0, %2;" : "=r"(P) : "r"(kk), "r"(lc.sp));
        asm("prmt.b32 %0, %1, 0, %2;" : "=r"(S) : "r"(kk), "r"(lc.ss));
#pragma unroll
        for (int k = 0; 2 * k < T1 - TC + 4; k++) ldsm_x4(bq + 4 * k, lc.uc + (TC - 8) * 256 + 512 * k);
#pragma unroll
        for (int k = 0; 4 * k < T1 - TC; k++) ldsm_x4(bq + 20 + 4 * k, lc.ud + (TC - 8) * 256 + 1024 * k);
        CST(3);
        mbar_wait(cnt + 8 * c, 0);
        mbar_wait(cnt + 40, 0);
        CST(4);
        float acc[6][4] = {};
        uint32_t a[PD + 1][4];
#pragma unroll
        for (int i = -PD; i < NS + 3; i++) {
            if (i + PD < NS) ldsm_x4_t(a[(i + PD) % (PD + 1)], seq[i + PD] < 32 ? lc.a4 + (seq[i + PD] - 2) * 128 : lc.a8 + (seq[i + PD] - 34) * 256);
            if (i < 0) continue;
#pragma unroll
            for (int T = T0; T < T1; T++) {
                if (i >= NS) break;
                const int ee = seq[i] < 32 ? 2 * T - 6 - seq[i] : T + 35 - seq[i];
                if (i == 0 && T >= TC) mma_bf16(acc[T - T0], P, 0u, S, P, bq[2 * (T - TC)], bq[2 * (T - TC) + 1]);
                if (i == 1 && T >= TC) mma_bf16_k8(acc[T - T0], 0u, S, bq[20 + T - TC]);
                if (i == (T >= TC ? 2 : 0)) mma_bf16(acc[T - T0], f[19].x, 0u, f[19].y, f[19].x, bq[2 * (T - TC + 4)], bq[2 * (T - TC + 4) + 1]);
                if (seq[i] < 32 ? ee >= 0 && ee <= 9 : ee >= 10) mma_bf16(acc[T - T0], a[i % (PD + 1)][0], a[i % (PD + 1)][1], a[i % (PD + 1)][2], a[i % (PD + 1)][3], f[ee].x, f[ee].y);
            }
#pragma unroll
            for (int k = 0; k < 3; k++) {
                const int o = 256 * T0 + 512 * k;
                auto at = [&](int d) { return i - d >= 0 && i - d < NS && seq[i - d < 0 ? 0 : i - d < NS ? i - d : 0] == 2 * T0 + 4 * k - 4; };
                if (at(CV_D2)) {
                    cv_store(dq + lc.go + o, xv, yv);
                    if (layer > 19 - 2 * k) __trap();
                }
                if (at(-2)) { ldsm_x4_t(yw, lc.y + o); ldsm_x4_t(yz, lc.y + 3584 + o); }
                if (at(1)) {
#pragma unroll
                    for (int q = 0; q < 4; q++) yw[q] = add2(add2(yw[q], yz[q]), pack2(acc[2 * k + (q >> 1)][2 * (q & 1)], acc[2 * k + (q >> 1)][2 * (q & 1) + 1]));
                    stsm_x4_t(lc.y + o, yw[0], yw[1], yw[2], yw[3]);
                    xv = lds4(smem_u32(Xs + c * XLEN) + o + lane * 16);
                    __syncwarp();
                    yv = lds4(smem_u32(sm + CV_SM_Y) + c * 8192 + o + usw(lane) * 16);
                    if (layer > 20 - 2 * k) __trap();
                    if (k == 2) CST(6);
                }
            }
        }
    };
    TSTAMP1X(9, 256);
    if (threadIdx.x >= 256) {
        CV_IDX
        const int t2 = tid - 256, wgu = (warp >> 2) & 1, g = lane >> 2, ti = lane & 3;
        if (t2 == 0) {
            mbar_init(cnt + 48, 1);
            asm volatile("fence.mbarrier_init.release.cluster;" ::: "memory");
            mbar_expect_tx(cnt + 48, CV_CPB * 2048);
            bulk_load(smem_u32(sm + CV_SM_O), tap + d0 * 128, CV_CPB * 2048, cnt + 48);
        } else if (lane == 0) {
            if (warp < 15) mbar_init(cnt + 8 * (warp - 9), warp == 14 ? 8 : 4);
            else if (layer) prefetch_tmap(&tmOut);
        }
        if (t2 < 140) {
            const int k = t2;
            const int off = k < 20 ? CV_SM_B + BX_5 + 8 * k : k < 40 ? CV_SM_B + BX_3 + 8 * (k - 20) : k < 74 ? CV_SM_B + BX_9 + 8 * (k - 40) : k < 108 ? CV_SM_B + BX_7 + 8 * (k - 74) : CV_SM_U + 8 * (k - 108);
            const int str = k < 108 ? BX_LEN : ULEN * 2;
#pragma unroll
            for (int c = 0; c < CV_CPB; c++) *reinterpret_cast<uint2*>(sm + off + c * str) = make_uint2(0, 0);
        }
        fence_async_smem();
        asm volatile("bar.arrive 3, 512;" ::: "memory");
        asm volatile("bar.sync 1, 256;" ::: "memory");
        TSTAMP1X(10, 256);
        asm volatile("setmaxnreg.inc.sync.aligned.u32 168;");
        const int hc = wgu ? warp & 3 : 4;
        const Lc lc = lane_consts(lane, hc);
        const uint32_t* E2[3];
#pragma unroll
        for (int k = 0; k < 3; k++) {
            const int i = min(t2 + 256 * k, 759), h = i / 76;
            E2[k] = reinterpret_cast<const uint32_t*>(sm + CV_SM_O) + 3 + i + (h >> 1) * 360 + (h & 1) * 52;
        }
        mbar_wait(cnt + 48, 0);
        TSTAMP1X(11, 256);
        {
            uint32_t w[3][4];
#pragma unroll
            for (int k = 0; k < 3; k++) { w[k][0] = E2[k][0]; w[k][1] = E2[k][1]; w[k][2] = E2[k][64]; w[k][3] = E2[k][65]; }
#pragma unroll
            for (int k = 0; k < 3; k++)
                *reinterpret_cast<uint4*>(sm + CV_SM_T + min(t2 + 256 * k, 759) * 16) =
                    make_uint4(__byte_perm(w[k][1], w[k][0], 0x7610), __byte_perm(w[k][3], w[k][2], 0x7610), __byte_perm(w[k][1], 0, 0x1032), __byte_perm(w[k][3], 0, 0x1032));
        }
        asm volatile("bar.sync 1, 256;" ::: "memory");
        const uint2* Tc = reinterpret_cast<const uint2*>(sm + CV_SM_T) + 16 + 76 * (warp & 2) + 8 * (warp & 1) + g - 2 * ti;
        uint2 fa[8][2], fn[8][2];
        auto near_taps = [&](uint2 (&f)[8][2], int c) {
#pragma unroll
            for (int m = 0; m < 8; m++) { f[m][0] = Tc[c * (TAPB / 8) + 16 * m]; f[m][1] = Tc[c * (TAPB / 8) + 16 * m - 8]; }
        };
        near_taps(fa, 3 * wgu);
        near_taps(fn, 2 - wgu);
        TSTAMP1X(12, 256); CST(0);
        uint32_t ya = smem_u32(sm + CV_SM_Y) + wgu * 8192 + (warp & 2) * 2048 + usw(2 * lane + (warp & 1)) * 16;
        uint64_t db = make_desc(smem_u32(Us + wgu * ULEN + UPADF), 16, 256, 3);
        if (wgu) asm volatile("bar.sync 6, 384;" ::: "memory");
        int c = wgu;
        auto chain = [&](const uint2 (&f)[8][2], auto&& meanwhile) {
            float acc[64];
            asm volatile("bar.sync %0, %1;" ::"r"(c ? 4 + wgu : 2), "r"(c ? 256 : 384) : "memory");
            TSTAMPC(1 + 3 * c);
            wgmma_fence();
#pragma unroll
            for (int m = 0; m < 8; m++) {
                wgmma_rs128(acc, f[m][0], f[m][1], db - (uint64_t)(2 * m), m);
                if (m == CV_HAND && c < 4) asm volatile("bar.arrive %0, 256;" ::"r"(5 - wgu) : "memory");
            }
            wgmma_commit();
            asm volatile("griddepcontrol.launch_dependents;" ::: "memory");
            TSTAMPC(2 + 3 * c); CST(13 + (c >> 1));
            meanwhile();
            wgmma_wait<0>();
            TSTAMPC(3 + 3 * c); CST(10 + (c >> 1));
            uint32_t w[16];
#pragma unroll
            for (int j = 0; j < 16; j++) w[j] = j ? pack2(acc[4 * j] + acc[4 * j - 2], acc[4 * j + 1] + acc[4 * j - 1]) : pack2(acc[0], acc[1]);
#pragma unroll
            for (int j = 0; j < 16; j += 4) stsm_x4_t(ya + 256 * j, w[j], w[j + 1], w[j + 2], w[j + 3]);
            __syncwarp();
            if (lane == 0) mbar_arrive(cnt + 8 * c);
            c += 2; ya += 16384; db += ULEN / 4;
        };
        const uint32_t e4 = lc.e4, e8 = e4 + 428 - 4 * g;
        uint2 fl[4];
        uint32_t kk;
#pragma unroll 1
        for (;;) {
            if (c != 1) chain(fa, [&] {
                if (c == 3 || warp + c == 12) {
#pragma unroll
                    for (int k = 0; k < 19; k++) (k < 16 ? fn[(k >> 1) & 7][k & 1] : fl[k & 3]) = make_uint2(lds1(k < 10 ? e4 + 32 * k + 16 : e8 + 32 * k - 304), lds1(k < 10 ? e4 + 32 * k : e8 + 32 * k - 320));
                    fl[3] = make_uint2(lds1(lc.en), lds1(lc.en - 64));
                    kk = lds1(smem_u32(sm + CV_SM_O) + 2048 * hc + 1672);
                }
            });
            if (c > 4) break;
            if (c == 2) asm volatile("bar.sync 7, 384;" ::: "memory");
            chain(fn, [&] { if (c == 2) near_taps(fa, 4); });
        }
        TSTAMP1X(6, 256); CST(2);
        if (wgu || warp == 8) {
            constexpr int seq[29] = {5, 6, 32, 7, 33, 8, 34, 9, 35, 10, 36, 11, 12, 13, 14, 15, 16, 17, 37, 18, 38, 19, 20, 21, 39, 22, 40, 23, 24};
            uint2 f[20];
#pragma unroll
            for (int k = 0; k < 20; k++) f[k] = k < 16 ? fn[(k >> 1) & 7][k & 1] : fl[k & 3];
            far(Int<10>(), seq, lc, hc, lane, f, kk);
        }
    } else {
        asm volatile("setmaxnreg.dec.sync.aligned.u32 88;");
        CV_IDX
        const uint4* ppv = piv + tid;
        const float4* psv = sum + tid;
        const uint2* pxv = reinterpret_cast<const uint2*>(x1T + (size_t)d0 * XCP) + (tid >> 4) * 32 + (tid & 15);
        asm volatile("st.shared.u64 [%0], %1;" ::"r"(smem_u32(Xs) + tid * 16), "l"((uint64_t)ppv ^ (uint64_t)psv ^ (uint64_t)pxv) : "memory");
        const int tc = (0x04302100 >> (4 * warp)) & 7;
        const Lc lc = lane_consts(lane, tc);
        pdl_sync();
        SPAN(3 + 4 * layer, 1);
        TSTAMP(0); CST(0);
        if (tid == 0) TSTAMPC(0);
        if (threadIdx.x == 0) { GSTAMP(g_tim, 15); }
        float4 sv[4];
#pragma unroll
        for (int k = 0; k < 4; k++)
            asm volatile("ld.relaxed.gpu.global.v4.f32 {%0,%1,%2,%3}, [%4];" : "=f"(sv[k].x), "=f"(sv[k].y), "=f"(sv[k].z), "=f"(sv[k].w) : "l"(psv + 256 * k) : "memory");
        uint4 pv;
        asm volatile("ld.relaxed.gpu.global.v4.u32 {%0,%1,%2,%3}, [%4];" : "=r"(pv.x), "=r"(pv.y), "=r"(pv.z), "=r"(pv.w) : "l"(ppv) : "memory");
        uint2 xe[CV_CPB], xo[CV_CPB];
#pragma unroll
        for (int c = 0; c < CV_CPB; c++) {
            asm volatile("ld.relaxed.gpu.global.v2.u32 {%0,%1}, [%2];" : "=r"(xe[c].x), "=r"(xe[c].y) : "l"(pxv + c * (XCP / 4)) : "memory");
            asm volatile("ld.relaxed.gpu.global.v2.u32 {%0,%1}, [%2];" : "=r"(xo[c].x), "=r"(xo[c].y) : "l"(pxv + c * (XCP / 4) + 16) : "memory");
        }
        constexpr float idm = 1.0f / DM;
        uint32_t mw[4];
        float rs[8];
#pragma unroll
        for (int k = 0; k < 4; k++) {
            const uint32_t pw = k == 0 ? pv.x : k == 1 ? pv.y : k == 2 ? pv.z : pv.w;
            const float d0_ = sv[k].x * idm, d1_ = sv[k].z * idm;
            mw[k] = pack2(__uint_as_float(pw << 16) + d0_, __uint_as_float(pw & 0xffff0000u) + d1_);
            const uint32_t vr = pack2(fmaxf(fmaf(-d0_, d0_, sv[k].y * idm), 0.f), fmaxf(fmaf(-d1_, d1_, sv[k].w * idm), 0.f));
            const uint32_t ve = pack2(__uint_as_float(vr << 16) + 1e-5f, __uint_as_float(vr & 0xffff0000u) + 1e-5f);
            const uint32_t sd = pack2(sqrt_apx(__uint_as_float(ve << 16)), sqrt_apx(__uint_as_float(ve & 0xffff0000u)));
            rs[2 * k] = rcp_apx(__uint_as_float(sd << 16)); rs[2 * k + 1] = rcp_apx(__uint_as_float(sd & 0xffff0000u));
        }
        if (rs[0] != 123.f) TSTAMP(13);
        const uint32_t ua = smem_u32(Us) + usw(tid + UPADF / 8) * 16;
        uint32_t uw[CV_CPB][4];
#pragma unroll
        for (int c = 0; c < CV_CPB; c++) {
            const uint32_t e0 = sub2(xe[c].x, mw[0]), e1 = sub2(xe[c].y, mw[1]), o0 = sub2(xo[c].x, mw[2]), o1 = sub2(xo[c].y, mw[3]);
            uw[c][0] = pack2(__uint_as_float(e0 << 16) * rs[0], __uint_as_float(o0 << 16) * rs[4]); uw[c][1] = pack2(__uint_as_float(e0 & 0xffff0000u) * rs[1], __uint_as_float(o0 & 0xffff0000u) * rs[5]);
            uw[c][2] = pack2(__uint_as_float(e1 << 16) * rs[2], __uint_as_float(o1 << 16) * rs[6]); uw[c][3] = pack2(__uint_as_float(e1 & 0xffff0000u) * rs[3], __uint_as_float(o1 & 0xffff0000u) * rs[7]);
            asm volatile("st.shared.v4.u32 [%0], {%1,%2,%3,%4};" ::"r"(ua + c * ULEN * 2), "r"(uw[c][0]), "r"(uw[c][1]), "r"(uw[c][2]), "r"(uw[c][3]) : "memory");
            if (c < 2) {
                fence_async_smem();
                asm volatile("bar.arrive %0, 384;" ::"r"(2 + 4 * c) : "memory");
                if (layer > 29 - c) __trap();
            }
        }
        fence_async_smem();
#pragma unroll
        for (int c = 0; c < CV_CPB; c++) *reinterpret_cast<uint4*>(Xs + c * XLEN + tid * 8) = make_uint4(xe[c].x, xe[c].y, xo[c].x, xo[c].y);
        asm volatile("bar.arrive 7, 384;" ::: "memory");
        asm volatile("bar.sync 3, 512;" ::: "memory");
        TSTAMP(1); CST(1);
        {
            auto box = [&](auto c0, auto c1, int chunk, int cb, bool full) {
                const uint32_t ea = smem_u32(Us + cb * ULEN) + usw(chunk + UPADF / 8 + (lane ? 1 : -1)) * 16, bx = smem_u32(sm + CV_SM_B + cb * BX_LEN) + chunk * 16;
                uint32_t lo[CV_CPB][4], hi[CV_CPB][2];
#pragma unroll
                for (int c = c0; c < c1; c++) {
                    lo[c][0] = 0;
#pragma unroll
                    for (int k = 1; k < 4; k++) lo[c][k] = __shfl_up_sync(~0u, uw[c][k], 1);
#pragma unroll
                    for (int k = 0; k < 2; k++) hi[c][k] = __shfl_down_sync(~0u, uw[c][k], 1);
                }
#pragma unroll
                for (int c = c0; c < c1; c++)
                    asm volatile("{\n.reg .pred p, q;\nsetp.eq.s32 p, %7, 0;\nsetp.eq.s32 q, %7, 31;\n@p ld.shared.v4.u32 {%0,%1,%2,%3}, [%6];\n@q ld.shared.v2.u32 {%4,%5}, [%6];\n}"
                                 : "+r"(lo[c][0]), "+r"(lo[c][1]), "+r"(lo[c][2]), "+r"(lo[c][3]), "+r"(hi[c][0]), "+r"(hi[c][1]) : "r"(ea + c * ULEN * 2), "r"(lane) : "memory");
#pragma unroll
                for (int c = c0; c < c1; c++) {
                    const uint32_t e[9] = {lo[c][1], lo[c][2], lo[c][3], uw[c][0], uw[c][1], uw[c][2], uw[c][3], hi[c][0], hi[c][1]};
                    uint32_t o[8], p[8], t[7], b3[5], b5[7];
#pragma unroll
                    for (int i = 0; i < 8; i++) { o[i] = __byte_perm(e[i], e[i + 1], 0x5432); p[i] = add2(e[i], o[i]); }
#pragma unroll
                    for (int i = 0; i < 5; i++) b3[i] = add2(o[i], p[i + 1]);
                    sts4(bx + c * BX_LEN + BX_3 + 160, b3);
#pragma unroll
                    for (int i = 1; i < 7; i++) { t[i] = add2(p[i], p[i + 1]); b5[i] = add2(t[i], e[i + 2]); }
                    sts4(bx + c * BX_LEN + BX_5 + 160, b5 + 2);
                    if (full) {
#pragma unroll
                        for (int i = 1; i < 5; i++) { b3[i] = add2(b3[i], t[i + 2]); t[i] = add2(t[i], b5[i + 2]); }
                        sts4(bx + c * BX_LEN + BX_7 + 272, b3 + 1);
                        sts4(bx + c * BX_LEN + BX_9 + 272, t + 1);
                    }
                }
            };
            auto reload = [&](int c, uint32_t a) { const uint4 v = lds4(a); uw[c][0] = v.x; uw[c][1] = v.y; uw[c][2] = v.z; uw[c][3] = v.w; };
            if (warp >= 6) {
#pragma unroll
                for (int c = 0; c < 3; c++) reload(c, ua - 1024 + (c + 2) * ULEN * 2);
            }
            if (warp >= 4) {
#pragma unroll
                for (int c = 3; c < 5; c++) reload(c, ua - 2048 + c * ULEN * 2);
            }
            box(Int<0>(), Int<3>(), warp < 6 ? tid : tid - 64, warp < 6 ? 0 : 2, warp < 4);
            if (warp >= 4) box(Int<3>(), Int<5>(), tid - 128, 0, true);
            else if (tid >= 128 - CV_CPB) {
                const int c = 127 - tid;
                const uint2 v = *reinterpret_cast<const uint2*>(Us + c * ULEN + UPADF);
                const float s1 = __uint_as_float(v.x << 16), s2 = s1 + __uint_as_float(v.x & 0xffff0000u), s3 = s2 + __uint_as_float(v.y << 16), s4 = s3 + __uint_as_float(v.y & 0xffff0000u);
                unsigned char* bc = sm + CV_SM_B + c * BX_LEN;
                *reinterpret_cast<uint32_t*>(bc + BX_5 + 156) = pack2(s1, s2);
                *reinterpret_cast<uint2*>(bc + BX_7 + 264) = make_uint2(v.x << 16, pack2(s2, s3));
                *reinterpret_cast<uint2*>(bc + BX_9 + 264) = make_uint2(pack2(s1, s2), pack2(s3, s4));
            }
        }
        __syncwarp();
        if (lane == 0) mbar_arrive(cnt + 40);
        TSTAMP(2); CST(2);
        if (layer && blockIdx.x == 0 && tid == 224) g_epoch = ld_epoch();
        __syncwarp();
        if ((0x6e >> warp) & 1) {
            constexpr int seq[16] = {0, 1, 2, 3, 4, 5, 6, 32, 7, 8, 9, 33, 10, 34, 11, 12};
            uint2 f[20];
            mbar_wait(cnt, 0);
            const uint32_t e8 = lc.e4 + 428 - (lane & 28);
#pragma unroll
            for (int k = 0; k < 13; k++) f[k] = make_uint2(lds1(k < 10 ? lc.e4 + 32 * k + 16 : e8 + 32 * k - 304), lds1(k < 10 ? lc.e4 + 32 * k : e8 + 32 * k - 320));
            f[19] = make_uint2(lds1(lc.en), lds1(lc.en - 64));
            far(Int<4>(), seq, lc, tc, lane, f, lds1(smem_u32(sm + CV_SM_O) + 2048 * tc + 1672));
        }
    }
    {
        CV_IDX
        if ((0xc91 >> warp) & 1) {
            const int c = __popc(0xc91 & ((1 << warp) - 1));
            uint4 xv[2], yv[2];
#pragma unroll
            for (int k = 0; k < 2; k++) xv[k] = lds4(smem_u32(Xs + c * XLEN) + 512 * k + lane * 16);
            const uint32_t u0 = lds1(smem_u32(Us + c * ULEN) + (lane == 31 ? UPADF * 2 : 0));
            mbar_wait(cnt + 8 * c, 0);
#pragma unroll
            for (int k = 0; k < 2; k++) yv[k] = lds4(smem_u32(sm + CV_SM_Y) + c * 8192 + 512 * k + usw(lane) * 16);
            const uint4 yz = lds4(smem_u32(sm + CV_SM_Y) + c * 8192 + 4096 + usw(lane) * 16);
            const float kk = __uint_as_float(lds1(smem_u32(sm + CV_SM_O) + 2048 * c + 1272) << 16);
            yv[1].x = add2(yv[1].x, yz.x); yv[1].y = add2(yv[1].y, yz.y); yv[1].z = add2(yv[1].z, yz.z);
            yv[1].w = pack2(fmaf(kk, __uint_as_float(u0 << 16), __uint_as_float(yv[1].w << 16) + __uint_as_float(yz.w << 16)),
                            fmaf(kk, __uint_as_float(u0 << 16) + __uint_as_float(u0 & 0xffff0000u), __uint_as_float(yv[1].w & 0xffff0000u) + __uint_as_float(yz.w & 0xffff0000u)));
#pragma unroll
            for (int k = 0; k < 2; k++) cv_store(dq + c * XCP * 2 + (lane >> 4) * 256 + (lane & 15) * 8 + 512 * k, xv[k], yv[k]);
        }
        TSTAMP(4); CST(8);
        if (layer == 1) {
            const int rb = (blockIdx.x >> 3) + (warp & 8) * 2, cg = blockIdx.x & 7, ch = (tid >> 3) & 31;
            const bf16* src = dst + (size_t)(cg * 80 + ch) * XCP + rb * 64 + (tid & 7) * 8;
            uint32_t v[3][4];
            __syncthreads();
            if (warp & 8) { const uint32_t c0 = clock(); while (clock() - c0 < 300) ; }
            uint32_t todo = (warp & 4) ? 3 : 7;
#pragma unroll 1
            for (int it = 0; it < SPIN_MAX; it++) {
#pragma unroll
                for (int k = 0; k < 3; k++)
                    if (todo >> k & 1)
                        asm volatile("ld.relaxed.gpu.global.v4.u32 {%0,%1,%2,%3}, [%4];" : "=r"(v[k][0]), "=r"(v[k][1]), "=r"(v[k][2]), "=r"(v[k][3]) : "l"(src + k * (32 * XCP)) : "memory");
#pragma unroll
                for (int k = 0; k < 3; k++)
                    if ((todo >> k & 1) && v[k][0] != ~0u && v[k][1] != ~0u && v[k][2] != ~0u && v[k][3] != ~0u) {
                        *reinterpret_cast<uint4*>(sm + (32 * k + ch) * 272 + ((tid & 7) + (warp & 8)) * 16) = make_uint4(v[k][0], v[k][1], v[k][2], v[k][3]);
                        todo ^= 1u << k;
                    }
                if (!todo) break;
                __nanosleep(CV_SLEEP);
            }
            __syncwarp();
            asm volatile("bar.sync %0, 256;" ::"r"(8 + (warp >> 3)) : "memory");
            uint32_t w[12];
#pragma unroll
            for (int k = 0; k < 3; k++) ldsm_x4(&w[4 * k], smem_u32(sm) + min(32 * k + lane, 79) * 272 + warp * 16);
            const uint32_t ot = smem_u32(sm + CV_SM_O) + warp * 1280, oa = ot + (lane & 7) * 160 + (lane >> 3) * 16;
            stsm_x4_t(oa, w[0], w[1], w[2], w[3]);
            stsm_x4_t(oa + 64, w[4], w[5], w[6], w[7]);
            asm volatile("stmatrix.sync.aligned.m8n8.x2.trans.shared.b16 [%0], {%1,%2};" ::"r"(oa + 128), "r"(w[8]), "r"(w[9]) : "memory");
            fence_async_smem();
            __syncwarp();
            if (lane == 0) {
                asm volatile("cp.async.bulk.tensor.3d.global.shared::cta.bulk_group [%0, {%1, %2, %3}], [%4];" ::"l"(&tmOut), "r"(cg * 80), "r"((rb >> 1) * 64 + 8 * (warp & 7)), "r"(rb & 1), "r"(ot) : "memory");
                asm volatile("cp.async.bulk.commit_group;" ::: "memory");
                asm volatile("cp.async.bulk.wait_group.read 0;" ::: "memory");
            }
        }
    }
    TSTAMP(3); CST(9); CST_END;
    GSTAMP(g_tim, 14);
    SPAN(3 + 4 * layer, 3);
}

template <int TA, int TB>
__device__ __forceinline__ void wgmma_n240(float (&d)[120], uint64_t da, uint64_t db, int acc) {
    asm volatile("{\n.reg .pred p;\nsetp.ne.b32 p, %124, 0;\nwgmma.mma_async.sync.aligned.m64n240k16.f32.bf16.bf16 {%0,%1,%2,%3,%4,%5,%6,%7,%8,%9,%10,%11,%12,%13,%14,%15,%16,%17,%18,%19,%20,%21,%22,%23,%24,%25,%26,%27,%28,%29,%30,%31,%32,%33,%34,%35,%36,%37,%38,%39,%40,%41,%42,%43,%44,%45,%46,%47,%48,%49,%50,%51,%52,%53,%54,%55,%56,%57,%58,%59,%60,%61,%62,%63,%64,%65,%66,%67,%68,%69,%70,%71,%72,%73,%74,%75,%76,%77,%78,%79,%80,%81,%82,%83,%84,%85,%86,%87,%88,%89,%90,%91,%92,%93,%94,%95,%96,%97,%98,%99,%100,%101,%102,%103,%104,%105,%106,%107,%108,%109,%110,%111,%112,%113,%114,%115,%116,%117,%118,%119}, %120, %121, p, 1, 1, %122, %123;\n}"
                 : "+f"(d[0]), "+f"(d[1]), "+f"(d[2]), "+f"(d[3]), "+f"(d[4]), "+f"(d[5]), "+f"(d[6]), "+f"(d[7]), "+f"(d[8]), "+f"(d[9]), "+f"(d[10]), "+f"(d[11]), "+f"(d[12]), "+f"(d[13]), "+f"(d[14]), "+f"(d[15]), "+f"(d[16]), "+f"(d[17]), "+f"(d[18]), "+f"(d[19]), "+f"(d[20]), "+f"(d[21]), "+f"(d[22]), "+f"(d[23]), "+f"(d[24]), "+f"(d[25]), "+f"(d[26]), "+f"(d[27]), "+f"(d[28]), "+f"(d[29]), "+f"(d[30]), "+f"(d[31]), "+f"(d[32]), "+f"(d[33]), "+f"(d[34]), "+f"(d[35]), "+f"(d[36]), "+f"(d[37]), "+f"(d[38]), "+f"(d[39]), "+f"(d[40]), "+f"(d[41]), "+f"(d[42]), "+f"(d[43]), "+f"(d[44]), "+f"(d[45]), "+f"(d[46]), "+f"(d[47]), "+f"(d[48]), "+f"(d[49]), "+f"(d[50]), "+f"(d[51]), "+f"(d[52]), "+f"(d[53]), "+f"(d[54]), "+f"(d[55]), "+f"(d[56]), "+f"(d[57]), "+f"(d[58]), "+f"(d[59]), "+f"(d[60]), "+f"(d[61]), "+f"(d[62]), "+f"(d[63]), "+f"(d[64]), "+f"(d[65]), "+f"(d[66]), "+f"(d[67]), "+f"(d[68]), "+f"(d[69]), "+f"(d[70]), "+f"(d[71]), "+f"(d[72]), "+f"(d[73]), "+f"(d[74]), "+f"(d[75]), "+f"(d[76]), "+f"(d[77]), "+f"(d[78]), "+f"(d[79]), "+f"(d[80]), "+f"(d[81]), "+f"(d[82]), "+f"(d[83]), "+f"(d[84]), "+f"(d[85]), "+f"(d[86]), "+f"(d[87]), "+f"(d[88]), "+f"(d[89]), "+f"(d[90]), "+f"(d[91]), "+f"(d[92]), "+f"(d[93]), "+f"(d[94]), "+f"(d[95]), "+f"(d[96]), "+f"(d[97]), "+f"(d[98]), "+f"(d[99]), "+f"(d[100]), "+f"(d[101]), "+f"(d[102]), "+f"(d[103]), "+f"(d[104]), "+f"(d[105]), "+f"(d[106]), "+f"(d[107]), "+f"(d[108]), "+f"(d[109]), "+f"(d[110]), "+f"(d[111]), "+f"(d[112]), "+f"(d[113]), "+f"(d[114]), "+f"(d[115]), "+f"(d[116]), "+f"(d[117]), "+f"(d[118]), "+f"(d[119])
                 : "l"(da), "l"(db), "n"(TA), "n"(TB), "r"(acc));
}

__device__ __forceinline__ void wgmma_n80(float (&d)[40], uint64_t da, uint64_t db, int acc) {
    asm volatile("{\n.reg .pred p;\nsetp.ne.b32 p, %42, 0;\nwgmma.mma_async.sync.aligned.m64n80k16.f32.bf16.bf16 {%0,%1,%2,%3,%4,%5,%6,%7,%8,%9,%10,%11,%12,%13,%14,%15,%16,%17,%18,%19,%20,%21,%22,%23,%24,%25,%26,%27,%28,%29,%30,%31,%32,%33,%34,%35,%36,%37,%38,%39}, %40, %41, p, 1, 1, 0, 1;\n}"
                 : "+f"(d[0]), "+f"(d[1]), "+f"(d[2]), "+f"(d[3]), "+f"(d[4]), "+f"(d[5]), "+f"(d[6]), "+f"(d[7]), "+f"(d[8]), "+f"(d[9]), "+f"(d[10]), "+f"(d[11]), "+f"(d[12]), "+f"(d[13]), "+f"(d[14]), "+f"(d[15]), "+f"(d[16]), "+f"(d[17]), "+f"(d[18]), "+f"(d[19]), "+f"(d[20]), "+f"(d[21]), "+f"(d[22]), "+f"(d[23]), "+f"(d[24]), "+f"(d[25]), "+f"(d[26]), "+f"(d[27]), "+f"(d[28]), "+f"(d[29]), "+f"(d[30]), "+f"(d[31]), "+f"(d[32]), "+f"(d[33]), "+f"(d[34]), "+f"(d[35]), "+f"(d[36]), "+f"(d[37]), "+f"(d[38]), "+f"(d[39])
                 : "l"(da), "l"(db), "r"(acc));
}

constexpr int A1_THREADS = 384;
constexpr int A1_NST = 4;
#define A1_SKEW 8
constexpr int A1_STAGE = 16384 + WQ_STAGE;
constexpr int A1_KVP = 336;
constexpr int A1_SM_KV = 2 * A1_STAGE;
constexpr int A1_SM_BAR = A1_NST * A1_STAGE;
constexpr int A1_SM_RS = A1_SM_BAR + 512;
constexpr int A1_SM_W0 = A1_SM_BAR + 3072, A1_SM_W3 = A1_SM_BAR - 3 * WOB, A1_SM_A1 = 2 * WOB, A1_SM_A0 = A1_SM_A1 + 61440;
constexpr int A1_SM_XA = A1_SM_W0 + 2 * WOB, A1_SM_XB = A1_SM_XA + 2048;
constexpr int A1_SMEM = A1_SM_W0 + 3 * WOB + CST_EXTRA;
static_assert(A1_SM_W3 >= A1_SM_KV + 144 * A1_KVP && A1_SM_W3 % 512 == 0 && A1_SM_A1 % 1024 == 0 && A1_SM_A0 <= A1_SM_KV && A1_SM_A0 + 61440 <= A1_SM_W3 && A1_SMEM <= 232448, "layout");
__device__ __forceinline__ constexpr uint32_t wo_off(int h) { return h * WOB + (h < 3 ? A1_SM_W0 : h < 6 ? A1_SM_W3 - 3 * WOB : -6 * WOB); }
#define A1_FRED "red.relaxed.gpu.global.add.u32"
#define A1_FLD "ld.acquire.gpu.global.u32"
#define ST_SLEEP 20
#define ST_SLEEP0 300
#define WO_LATE bar_done
#define A1_P0 2
#define A1_PW (kb - 2)
#define A1_FSPIN SPIN_MAX
#define A1_FSLEEP 40
#define YT_LAYER 1
#define WOT 352
#define A1_WOAT 6

template <int L>
__device__ __forceinline__ void a1_mainloop(float (&acc)[120], uint32_t sbase, uint32_t bars, int wg, int tile) {
    constexpr int layer = L; (void)layer;
    const uint64_t da0 = L ? make_desc(sbase + wg * 8192, 8192, 1024, 1) : make_desc(sbase + wg * 8192, 16, 1024, 1), db0 = make_desc(sbase + 16384, 1024, 256, 3);
#pragma unroll 1
    for (int t = 0;; t++) {
        const int st = t % A1_NST;
        mbar_wait(bars + 8 * st, (t / A1_NST) & 1);
        if (t == A1_SKEW && wg == 0) mbar_wait(bars + 160, 0);
        TSTAMP3(1 + t);
        if (t == 0) CSA(0);
        wgmma_fence();
#pragma unroll
        for (int kk = 0; kk < 4; kk++) wgmma_n240<L, 1>(acc, da0 + (uint32_t)(st * (A1_STAGE / 16) + kk * (L ? 128 : 2)), db0 + (uint32_t)(st * (A1_STAGE / 16) + (kk >> 1) * (WQ_STAGE / 32) + (kk & 1) * 32), kk ? 1 : t);
        wgmma_commit();
        if (t == 9) break;
        if (t == A1_SKEW - 1 && wg == 0) wgmma_wait<0>(); else wgmma_wait<1>();
        if (t > 0 && (threadIdx.x & 127) == 0) {
            if (t != A1_SKEW || wg) mbar_arrive(bars + 8 * (A1_NST + (t - 1) % A1_NST));
            if (t == A1_SKEW - 1 && wg == 0) mbar_arrive(bars + 8 * (A1_NST + t % A1_NST));
        }
    }
}

__global__ void __launch_bounds__(A1_THREADS, 1) a1_kernel(const int layer, const bf16* __restrict__ x0, const unsigned char* __restrict__ wq, const unsigned char* __restrict__ wo,
                                                           float2* __restrict__ rsum, uint4* __restrict__ of, const __grid_constant__ CUtensorMap tmX,
                                                           const __grid_constant__ CUtensorMap tmR, const __grid_constant__ CUtensorMap tmX1, const __grid_constant__ TileTab tab) {
    extern __shared__ __align__(1024) unsigned char stg[];
    const uint32_t sbase = smem_u32(stg);
    const uint32_t bars = sbase + A1_SM_BAR;
    const uint32_t bar_stat = bars + 64, bar_kv = bars + 72, bar_rd = bars + 168;
    const uint32_t bar_wo = bars + 208, bar_done = bars + 216, bar_pv = bars + 224, bar_kvf = bars + 232, bar_f2 = bars + 248, bar_e2 = bars + 384, que = bars + 448;
    const int tid = threadIdx.x;
    const int w = __shfl_sync(~0u, tid >> 5, 0), wg = w >> 2;
    uint32_t smid, ns;
    asm volatile("mov.u32 %0, %smid;" : "=r"(smid));
    asm volatile("mov.u32 %0, %nsmid;" : "=r"(ns));
    const auto te = tab.e[ns == tab.ns ? smid : 132 + blockIdx.x];
    const int tile = te.tile, mb = te.mb, hg = te.hg;
    float2* rst = reinterpret_cast<float2*>(stg + A1_SM_RS) + 8;
    auto issue_w = [&](int it) { bulk_load(sbase + (it % A1_NST) * A1_STAGE + 16384, wq + te.woff + it * WQ_STAGE, WQ_STAGE, bars + 8 * (it % A1_NST)); };
    auto issue_x = [&](int it, int kb) {
        asm volatile("cp.async.bulk.tensor.5d.shared::cluster.global.mbarrier::complete_tx::bytes [%0], [%1, {%3, %3, %3, %4, %5}], [%2];"
                     ::"r"(sbase + (it % A1_NST) * A1_STAGE), "l"(&tmX), "r"(bars + 8 * (it % A1_NST)), "r"(0), "r"(mb), "r"(kb) : "memory");
    };
    if (w == 8 && tile < 128) {
        const bool one = elect();
        if (one) {
#pragma unroll
            for (int i = 0; i < A1_NST; i++) mbar_init(bars + 8 * i, 1);
            asm volatile("fence.mbarrier_init.release.cluster;" ::: "memory");
        }
        __syncwarp();
        asm volatile("bar.arrive 0, 384;" ::: "memory");
        if (one) {
#define PW asm volatile("griddepcontrol.wait;" ::: "memory");
            if (layer) { issue_w(0); PW issue_x(0, te.kb0); issue_x(1, te.kb0 + 1); }
            else { issue_x(0, te.kb0); issue_x(1, te.kb0 + 1); PW issue_w(0); }
            issue_w(1);
#pragma unroll
            for (int i = 0; i < A1_NST; i++) mbar_expect_tx(bars + 8 * i, A1_STAGE);
            asm volatile("griddepcontrol.launch_dependents;" ::: "memory");
#pragma unroll
            for (int kb = 2; kb < A1_P0; kb++) { issue_x(kb, te.kb0 + kb); issue_w(kb); }
            DBGC(34); DBGV(33, smid); DBGV(40, t_entry); DBGV(30, t_a); DBGV(31, t_b); DBGV(32, t_c); DBGV(38, t_d); DBGV(39, t_e);
        }
    }
    if (tile >= 128) { sm_idle(layer); return; }
    if (wg == 2) {
        if (w != 8) {
            if (tid == 320) { prefetch_tmap(&tmX); prefetch_tmap(&tmR); prefetch_tmap(&tmX1); }
            asm volatile("bar.sync 0, 384;" ::: "memory");
        }
        if (w == 9) {
            asm volatile("bar.arrive 3, 64;" ::: "memory");
            if (layer == 0) pdl_sync();
            float4 a[2] = {};
#pragma unroll
            for (int k = 0; k < 10; k++)
#pragma unroll
                for (int h = 0; h < 2; h++) {
                    const int c4 = min(tid - 288 + 32 * h, 59);
                    const float4 v = __ldcg(reinterpret_cast<const float4*>(g_csp + k * 1920 + hg * 80) + c4 + (c4 / 20) * 140);
                    a[h].x += v.x; a[h].y += v.y; a[h].z += v.z; a[h].w += v.w;
                }
#pragma unroll
            for (int h = 0; h < 2; h++)
#pragma unroll
                for (int k = 0; k < 4; k++) {
                    const float c = 0.5f * (k == 0 ? a[h].x : k == 1 ? a[h].y : k == 2 ? a[h].z : a[h].w), c1 = c - rbf(c), c2 = c1 - rbf(c1);
                    *reinterpret_cast<uint4*>(stg + A1_SM_XB + (4 * min(tid - 288 + 32 * h, 59) + k) * 16) = make_uint4(pack2(c, c1), pack2(c2, 0.f), 0u, 0u);
                }
            fence_async_smem();
            __syncwarp();
            if (tid == 288) mbar_arrive(bar_stat);
#pragma unroll 4
            for (int k = 0; k < 40; k++) asm volatile("st.global.v4.u32 [%0], {%1,%1,%1,%1};" ::"l"(of + (mb * 8 + hg) * 1280 + 32 * k + (tid - 288)), "r"(~0u) : "memory");
            asm volatile("fence.acq_rel.gpu;" ::: "memory");
            asm volatile("fence.proxy.async.global;" ::: "memory");
            __syncwarp();
            if (tid == 288) mbar_arrive(bar_done);
            if (layer == YT_LAYER) {
#pragma unroll 4
                for (int k = tid - 288; k < 5 * XCP / 8; k += 32) asm volatile("st.global.v4.u32 [%0], {%1,%1,%1,%1};" ::"l"(reinterpret_cast<uint4*>(g_yT) + tile * (5 * XCP / 8) + k), "r"(~0u) : "memory");
            }
            TSTAMP1T(9, 288);
        } else if (w == 8) {
            asm volatile("bar.sync 3, 64;" ::: "memory");
            if (elect()) {
#pragma unroll 1
                for (int kb = A1_P0; kb < 10; kb++) {
                    if (kb < A1_NST) mbar_wait(bars + 8 * A1_PW, 0);
                    else {
                        mbar_wait(bars + 8 * (A1_NST + kb % A1_NST), ((kb / A1_NST) - 1) & 1);
                        if (layer && kb < 9) mbar_wait(bar_rd + 8 * (kb - A1_NST), 0);
                        mbar_expect_tx(bars + 8 * (kb % A1_NST), A1_STAGE);
                    }
                    issue_x(kb, kb < 5 ? kb + te.kb0 : kb - te.kb0); issue_w(kb);
                    if (kb == A1_WOAT) {
                        mbar_expect_tx(bar_wo, 8 * WOB);
                        bulk_load(sbase + A1_SM_W0, wo + hg * 8 * WOB, 2 * WOB, bar_wo);
                    }
                }
                TSTAMP1T(6, 256);
                mbar_wait(bars + 8 * (A1_NST + 3), 1);
                bulk_load(sbase + A1_SM_W3, wo + (hg * 8 + 3) * WOB, 3 * WOB, bar_wo);
            }
            __syncwarp();
        } else {
            const int j = tid - 320;
            const uint32_t tag = ld_epoch();
            if (tid == 352) sm_started(layer);
            if (layer == 0) {
                const uint4* src = reinterpret_cast<const uint4*>(x0 + (size_t)(mb * 128 + hg * 16 + (j >> 2)) * DM);
                uint4 v[20];
#pragma unroll
                for (int k = 0; k < 20; k++) v[k] = __ldg(src + (j & 3) + 4 * k);
                const float p0 = __uint_as_float(__shfl_sync(~0u, v[0].x, j & 28) << 16);
                float s[2] = {0.f, 0.f}, q[2] = {0.f, 0.f};
#pragma unroll
                for (int k = 0; k < 20; k++) {
                    const uint32_t w[4] = {v[k].x, v[k].y, v[k].z, v[k].w};
#pragma unroll
                    for (int i = 0; i < 4; i++) {
                        const float a = __uint_as_float(w[i] << 16) - p0, b = __uint_as_float(w[i] & 0xffff0000u) - p0;
                        s[0] += a; s[1] += b; q[0] = fmaf(a, a, q[0]); q[1] = fmaf(b, b, q[1]);
                    }
                }
                float s0 = s[0] + s[1], q0 = q[0] + q[1];
#pragma unroll
                for (int o = 1; o <= 2; o <<= 1) { s0 += __shfl_xor_sync(~0u, s0, o); q0 += __shfl_xor_sync(~0u, q0, o); }
                if ((j & 3) == 0) {
                    const float d = s0 * (1.0f / DM);
                    const uint32_t ms = pack2(p0 + d, sqrt_apx(rbf(rbf(fmaxf(fmaf(-d, d, q0 * (1.0f / DM)), 0.f)) + 1e-5f)));
                    asm volatile("st.global.cg.u64 [%0], %1;" ::"l"(g_rstat + mb * 128 + (j & 4) * 16 + hg * 8 + (j >> 3)), "l"(tagw(ms, tag)) : "memory");
                    g_piv[mb * 128 + hg * 16 + ((j >> 2) & 8) + (j & 4) + ((j >> 3) & 3)] = __ushort_as_bfloat16((unsigned short)ms);
                }
            }
            float o[4];
            int row;
            if (layer == 0) {
                ulonglong2 v;
#pragma unroll 1
                for (int it = 0; it < SPIN_MAX; it++) {
                    v = ld_tag2(reinterpret_cast<const ulonglong2*>(g_rstat + mb * 128) + j);
                    if (tag_ok(v, tag)) break;
                    __nanosleep(100);
                }
                o[0] = __uint_as_float((uint32_t)v.x << 16); o[1] = rcp_apx(__uint_as_float((uint32_t)v.x & 0xffff0000u));
                o[2] = __uint_as_float((uint32_t)v.y << 16); o[3] = rcp_apx(__uint_as_float((uint32_t)v.y & 0xffff0000u));
                row = 2 * j;
            } else {
                const int ch = j & 7, kg = (j >> 3) & 3;
                const unsigned char* src = stg + (j >> 5) * 8192 + (hg & 3) * 2048;
                float s[8], q[8], p0[8];
#pragma unroll
                for (int i = 0; i < 8; i++) { s[i] = 0.f; q[i] = 0.f; }
#pragma unroll 1
                for (int it = 0; it < 5; it++) {
                    uint4 v[4];
                    mbar_wait(bars + 8 * (it % A1_NST), it / A1_NST);
#pragma unroll
                    for (int k = 0; k < 4; k++) v[k] = *reinterpret_cast<const uint4*>(src + (it % A1_NST) * A1_STAGE + (4 * k + kg) * 128 + ((ch ^ ((4 * k + kg) & 7)) << 4));
                    if (it == 0) {
                        const uint4 pv = *reinterpret_cast<const uint4*>(src + (ch << 4));
                        const uint32_t w[4] = {pv.x, pv.y, pv.z, pv.w};
#pragma unroll
                        for (int i = 0; i < 4; i++) { p0[2 * i] = __uint_as_float(w[i] << 16); p0[2 * i + 1] = __uint_as_float(w[i] & 0xffff0000u); }
                    }
                    asm volatile("" :: "r"(v[0].x), "r"(v[1].x), "r"(v[2].x), "r"(v[3].x), "f"(p0[0]) : "memory");
                    __syncwarp();
                    if ((tid & 31) == 0) mbar_arrive(bar_rd + 8 * it);
#pragma unroll
                    for (int k = 0; k < 4; k++) {
                        const uint32_t w[4] = {v[k].x, v[k].y, v[k].z, v[k].w};
#pragma unroll
                        for (int i = 0; i < 4; i++) {
                            const float a = __uint_as_float(w[i] << 16) - p0[2 * i], b = __uint_as_float(w[i] & 0xffff0000u) - p0[2 * i + 1];
                            s[2 * i] += a; s[2 * i + 1] += b; q[2 * i] = fmaf(a, a, q[2 * i]); q[2 * i + 1] = fmaf(b, b, q[2 * i + 1]);
                        }
                    }
                }
#pragma unroll
                for (int i = 0; i < 4; i++) {
                    const bool up = kg & 2;
                    const float ss = __shfl_xor_sync(~0u, up ? s[i] : s[i + 4], 16), qq = __shfl_xor_sync(~0u, up ? q[i] : q[i + 4], 16);
                    s[i] = (up ? s[i + 4] : s[i]) + ss; q[i] = (up ? q[i + 4] : q[i]) + qq; p0[i] = up ? p0[i + 4] : p0[i];
                }
#pragma unroll
                for (int i = 0; i < 2; i++) {
                    const bool up = kg & 1;
                    const float ss = __shfl_xor_sync(~0u, up ? s[i] : s[i + 2], 8), qq = __shfl_xor_sync(~0u, up ? q[i] : q[i + 2], 8);
                    s[i] = (up ? s[i + 2] : s[i]) + ss; q[i] = (up ? q[i + 2] : q[i]) + qq; p0[i] = up ? p0[i + 2] : p0[i];
                }
                uint4* gp = g_halo + 86016 + mb * 512 + j;
                const float d0 = s[0] * (1.0f / 80.0f), d1 = s[1] * (1.0f / 80.0f);
                asm volatile("st.relaxed.gpu.global.v4.f32 [%0], {%1,%2,%3,%4};" ::"l"(gp + hg * 64), "f"(p0[0] + d0), "f"(fmaxf(fmaf(-d0, s[0], q[0]), 0.f)), "f"(p0[1] + d1), "f"(fmaxf(fmaf(-d1, s[1], q[1]), 0.f)) : "memory");
                __nanosleep(ST_SLEEP0);
                uint32_t pw[8][4], todo = 0xff;
#pragma unroll 1
                for (int it = 0; it < SPIN_MAX; it++) {
#pragma unroll
                    for (int k = 0; k < 8; k++)
                        if (todo >> k & 1) asm volatile("ld.relaxed.gpu.global.v4.u32 {%0,%1,%2,%3}, [%4];" : "=r"(pw[k][0]), "=r"(pw[k][1]), "=r"(pw[k][2]), "=r"(pw[k][3]) : "l"(gp + k * 64) : "memory");
#pragma unroll
                    for (int k = 0; k < 8; k++)
                        if (__all_sync(~0u, pw[k][0] != ~0u && pw[k][1] != ~0u && pw[k][2] != ~0u && pw[k][3] != ~0u)) todo &= ~(1u << k);
                    if (!todo) break;
                    __nanosleep(ST_SLEEP);
                }
#pragma unroll
                for (int r = 0; r < 2; r++) {
                    float mean = 0.f, m2 = 0.f;
#pragma unroll
                    for (int k = 0; k < 8; k++) mean += __uint_as_float(pw[k][2 * r]);
                    mean *= 0.125f;
#pragma unroll
                    for (int k = 0; k < 8; k++) {
                        const float dm = __uint_as_float(pw[k][2 * r]) - mean;
                        m2 += fmaf(80.0f * dm, dm, __uint_as_float(pw[k][2 * r + 1]));
                    }
                    o[2 * r] = rbf(mean);
                    o[2 * r + 1] = rcp_apx(rbf(sqrt_apx(rbf(rbf(m2 * (1.0f / DM)) + 1e-5f))));
                }
                row = (j >> 5) * 64 + (j & 7) * 8 + ((j >> 3) & 3) * 2;
                if (hg == 0) *reinterpret_cast<uint32_t*>(g_piv + SEQ + mb * 128 + 2 * (row & 60) + 4 * (row >> 6) + (row & 3)) = __byte_perm(__float_as_uint(o[0]), __float_as_uint(o[2]), 0x7632);
            }
#pragma unroll
            for (int r = 0; r < 2; r++)
                *reinterpret_cast<uint4*>(stg + A1_SM_XA + (row + r) * 16) = make_uint4(__byte_perm(__float_as_uint(-o[2 * r]), 0, 0x3232), __float_as_uint(-o[2 * r]) >> 16, 0u, 0u);
            *reinterpret_cast<float4*>(rst + row + (row >> 6) * 8) = make_float4(o[0], o[1], o[2], o[3]);
            fence_async_smem();
            TSTAMP1T(7, 320);
            if (tid == 320) DBGC(44);
            __syncwarp();
            if ((tid & 31) == 0) mbar_arrive(bar_stat);
        }
        if (tid == 320) DBGCAL(0);
        if (tid == WOT) {
            mbar_wait(WO_LATE, 0);
            mbar_wait(bar_done, 0);
            bulk_load(sbase, wo + (hg * 8 + 6) * WOB, 2 * WOB, bar_wo);
            bulk_load(sbase + A1_SM_W0 + 2 * WOB, wo + (hg * 8 + 2) * WOB, WOB, bar_wo);
        }
        __syncwarp();
#define FWA 11
#define FWB 10
        if (w == FWA || w == FWB) {
            const int cw = w == FWB;
            const uint32_t* fl = reinterpret_cast<const uint32_t*>(rsum + 2 * SEQ) + (((layer * 16 + mb) * 2 + cw) * 8 + (tid & 7)) * FSTR;
            const unsigned char* src = reinterpret_cast<const unsigned char*>(of) + mb * 163840 + cw * 10240 + (tid & 7) * 20480;
            const uint32_t sl = sbase + (cw ? A1_SM_A1 : A1_SM_A0);
            mbar_wait(cw ? bar_done : bar_kvf, 0);
            if ((tid & 31) == 0) {
                mbar_expect_tx(bar_f2 + 64 * cw + 64, 10240);
                tma_load_3d(sl + 51200, &tmR, layer ? 0 : hg * 80, layer ? hg * 80 : mb * 64, layer ? mb * 2 + cw : cw, bar_f2 + 64 * cw + 64);
            }
            __syncwarp();
            uint32_t pend = 0xffu & ~(1u << hg), v = 0;
            const uint32_t bo = wo_off((tid & 7) + ((tid & 7) < hg)) >> 4, lt = (1u << (tid & 31)) - 1;
#pragma unroll 1
            for (int it = 0; pend && it < 2 * SPIN_MAX; it++) {
                if (v != 4 && (pend >> (tid & 31) & 1)) asm volatile(A1_FLD " %0, [%1];" : "=r"(v) : "l"(fl) : "memory");
                uint32_t fr;
                asm volatile("{\n.reg .pred p;\nmbarrier.test_wait.parity.shared::cta.b64 p, [%1], 0;\nselp.b32 %0, 1, 0, p;\n}" : "=r"(fr) : "r"(bar_e2 + 16 * cw + (tid & 1) * 8) : "memory");
                fr = __ballot_sync(~0u, fr);
                uint32_t m = __ballot_sync(~0u, v == 4 || it >= A1_FSPIN) & pend;
                const int q = 8 - __popc(pend) + __popc(m & lt);
                m &= __ballot_sync(~0u, q < ((fr & 2) ? 8 : (fr & 1) ? 7 : 5));
                pend ^= m;
                if (m >> (tid & 31) & 1) DBGC(12 + cw * 8 + (tid & 7));
                if (!m) __nanosleep(A1_FSLEEP);
                else asm volatile("fence.proxy.async.global;" ::: "memory");
                if (m >> (tid & 31) & 1) {
                    bulk_load(q == 7 && !cw ? sbase + A1_SM_W0 : sl + (q < 6 ? q : q - 6) * 10240, src, 10240, bar_f2 + 64 * cw + 8 * q);
                    asm volatile("st.shared.u32 [%0], %1;" ::"r"(que + 32 * cw + 4 * q), "r"(bo) : "memory");
                    mbar_expect_tx(bar_f2 + 64 * cw + 8 * q, 10240);
                    DBGC(44 + cw * 8 + q);
                }
                __syncwarp();
            }
        }
    } else {
        if (tid == 0) {
            mbar_init(bar_stat, 3);
#pragma unroll
            for (int i = 0; i < 8; i++) mbar_init(bar_kv + 8 * i, 1);
            mbar_init(bars + 144, 1);
            mbar_init(bars + 160, 1);
#pragma unroll
            for (int i = 0; i < 5; i++) mbar_init(bar_rd + 8 * i, 2);
            asm volatile("fence.mbarrier_init.release.cluster;" ::: "memory");
        } else if (tid == 32) {
            mbar_init(bar_wo, 1); mbar_init(bar_done, 3); mbar_init(bar_pv, 4); mbar_init(bar_kvf, 8);
#pragma unroll
            for (int i = 0; i < 4; i++) { mbar_init(bar_e2 + 8 * i, i == 1 ? 2 : 1); mbar_init(bars + 8 * (A1_NST + i), 2); }
            asm volatile("fence.mbarrier_init.release.cluster;" ::: "memory");
        } else if (tid == 96) {
#pragma unroll
            for (int i = 0; i < 4; i++) mbar_init(bars + 416 + 8 * i, 1);
            asm volatile("fence.mbarrier_init.release.cluster;" ::: "memory");
        } else if (tid == 64) {
#pragma unroll
            for (int i = 1; i <= 16; i++) mbar_init(bar_f2 + 8 * i, 1);
            asm volatile("fence.mbarrier_init.release.cluster;" ::: "memory");
        }
        asm volatile("bar.sync 0, 384;" ::: "memory");
        SPAN(1 + 4 * layer, 0);
        constexpr int on = 1;
        float acc[120];
        const int lane = tid & 31, warp = w & 7, g = lane >> 2, t = lane & 3;
        if (on) {
            SPAN(1 + 4 * layer, 1);
            TSTAMP1(0);
            if (threadIdx.x == 0) { GSTAMP(g_tim1, 15); }
            TSTAMP3(0);
            if (tid == 0) TSTAMP2(0);
            TSTAMP4(0);
            if (tid == 0) DBGC(60);
            if (layer == 0) a1_mainloop<0>(acc, sbase, bars, wg, tile); else a1_mainloop<1>(acc, sbase, bars, wg, tile);
            uint32_t ok;
            asm volatile("{\n.reg .pred p;\nmbarrier.test_wait.parity.shared::cta.b64 p, [%1], 0;\nselp.b32 %0, 1, 0, p;\n}" : "=r"(ok) : "r"(bar_stat) : "memory");
            if (tid == 128 && !ok) mbar_arrive(bars + 160);
            __syncwarp();
            mbar_wait(bar_stat, 0);
            wgmma_fence();
            wgmma_n240<0, 0>(acc, make_desc(sbase + A1_SM_XA + wg * 1024, 0, 128, 0), make_desc(sbase + A1_SM_XB, 0, 128, 0), 1);
            wgmma_commit();
            if (tid == 128 && ok) mbar_arrive(bars + 160);
            mbar_wait(bars + 8 * (A1_NST + 3), 1);
        }
        const float2* rw = rst + 16 * warp + 8 * wg;
        const float rb0 = rw[g + 8].y, ra = rw[g].y * 0.22360679774997896f, rb = rb0 * 0.22360679774997896f;
        wgmma_wait<0>();
        if ((tid & 127) == 0) mbar_arrive(bar_done);
        TSTAMP1(2); CSA(1);
        TSTAMP1T(13, 224);
        if ((tid & 127) == 0) DBGC(62 - wg);
        uint32_t f[2][30];
#pragma unroll
        for (int j = 10; j < 30; j++) f[1][j] = pack2(acc[4 * j + 2], acc[4 * j + 3]);
        if ((warp & 3) == 3) {
            uint4* hout = g_halo + (((layer * 16 + mb) * 8 + hg) * 2 + wg) * 168;
#pragma unroll
            for (int j = 0; j < 20; j += 4)
                asm volatile("st.relaxed.gpu.global.v4.u32 [%0], {%1,%2,%3,%4};" ::"l"(hout + 8 * j + lane), "r"(f[1][10 + j]), "r"(f[1][11 + j]), "r"(f[1][12 + j]), "r"(f[1][13 + j]) : "memory");
            if (t == 0) asm volatile("st.relaxed.gpu.global.f32 [%0], %1;" ::"l"(reinterpret_cast<float*>(hout + 160) + g), "f"(rb0) : "memory");
        }
        TSTAMP1T(12, 224);
        const uint32_t kvw = sbase + A1_SM_KV + (16 * warp + 8 * wg) * A1_KVP;
        const uint32_t mrow = kvw + (lane & 7) * A1_KVP + (lane >> 3) * 16;
#pragma unroll
        for (int j = 0; j < 20; j += 4) stsm_x4(mrow + 16 * A1_KVP + 16 * j, f[1][10 + j], f[1][11 + j], f[1][12 + j], f[1][13 + j]);
        __syncwarp();
        if (lane == 0 && (warp & 3) != 3) mbar_arrive(bar_kv + 8 * (warp + 1));
#pragma unroll
        for (int j = 0; j < 30; j++) f[0][j] = pack2(acc[4 * j], acc[4 * j + 1]);
        stsm_x4(mrow + 8 * A1_KVP + 160, f[0][20], f[0][21], f[0][22], f[0][23]);
        stsm_x4(mrow + 8 * A1_KVP + 224, f[0][24], f[0][25], f[0][26], f[0][27]);
        asm volatile("stmatrix.sync.aligned.m8n8.x2.shared.b16 [%0], {%1,%2};" ::"r"(mrow + 8 * A1_KVP + 288), "r"(f[0][28]), "r"(f[0][29]) : "memory");
#pragma unroll
        for (int j = 0; j < 10; j++) f[1][j] = pack2(acc[4 * j + 2], acc[4 * j + 3]);
        __syncwarp();
        uint32_t vb[10][2], vp[12], kp[12];
#pragma unroll
        for (int j = 0; j < 10; j += 2) ldsm_x4_t(&vb[j][0], kvw + (8 + (lane & 15)) * A1_KVP + 160 + (lane >> 4) * 16 + 16 * j);
        const bool up0 = 2 * t > g, up1 = 2 * t + 1 > g, edge = (mb | (warp & 3)) == 0;
        float rk[4];
        auto above = [&]() {
            mbar_wait(bar_kv + 8 * warp, 0);
#pragma unroll
            for (int j = 0; j < 12; j += 4) ldsm_x4(&kp[j], mrow + 16 * j);
            rk[0] = rw[2 * t - (up0 ? 8 : 0)].y; rk[1] = rw[2 * t + 1 - (up1 ? 8 : 0)].y;
#pragma unroll
            for (int j = 0; j < 12; j += 4) ldsm_x4_t(&vp[j], mrow + 160 + 16 * j - (j == 8 ? (lane & 16) * 2 : 0));
            __syncwarp();
            if (lane == 0) mbar_arrive(bar_kvf);
        };
        auto halo = [&]() {
            if (lane == 0) mbar_arrive(bar_kvf);
            const uint4* hin = g_halo + (((layer * 16 + mb - 1) * 8 + hg) * 2 + wg) * 168;
            uint32_t hv[22] = {};
            rk[0] = rw[2 * t].y; rk[1] = rw[2 * t + 1].y;
            if (mb > 0) {
#pragma unroll 1
                for (int it = 0; it < SPIN_MAX; it++) {
#pragma unroll
                    for (int k = 0; k < 20; k += 4)
                        asm volatile("ld.relaxed.gpu.global.v4.u32 {%0,%1,%2,%3}, [%4];" : "=r"(hv[k]), "=r"(hv[k + 1]), "=r"(hv[k + 2]), "=r"(hv[k + 3]) : "l"(hin + 8 * k + lane) : "memory");
                    asm volatile("ld.relaxed.gpu.global.v2.u32 {%0,%1}, [%2];" : "=r"(hv[20]), "=r"(hv[21]) : "l"(reinterpret_cast<const uint2*>(hin + 160) + t) : "memory");
                    uint32_t m = max(hv[20], hv[21]);
#pragma unroll
                    for (int k = 0; k < 20; k += 2) m = __vimax3_u32(m, hv[k], hv[k + 1]);
                    if (!__any_sync(~0u, m == ~0u)) break;
                }
            }
            if (tid == 0) mbar_arrive(bars + 144);
            if (lane == 0) DBGC(52 - 16 * wg);
#pragma unroll
            for (int j = 0; j < 10; j++) {
                kp[j] = hv[j];
                asm volatile("movmatrix.sync.aligned.m8n8.trans.b16 %0, %1;" : "=r"(vp[j]) : "r"(hv[10 + j]));
            }
            if (up0) rk[0] = __uint_as_float(hv[20]);
            if (up1) rk[1] = __uint_as_float(hv[21]);
        };
        rk[2] = rw[2 * t + (up0 ? 0 : 8)].y; rk[3] = rw[2 * t + 1 + (up1 ? 0 : 8)].y;
        uint32_t qs[4][2];
#pragma unroll
        for (int h = 0; h < 4; h++) {
            qs[h][0] = (t >> 1) == (h & 1) ? f[0][5 * (h >> 1) + 2] : 0u; qs[h][1] = (t >> 1) == (h & 1) ? f[1][5 * (h >> 1) + 2] : 0u;
            asm volatile("" : "+r"(qs[h][0]), "+r"(qs[h][1]));
        }
#pragma unroll
        for (int j = 0; j < 10; j++) asm volatile("" : "+r"(f[0][j]), "+r"(f[1][j]), "+r"(f[0][10 + j]));
        if (warp & 3) above(); else if (wg) halo();
        TSTAMP1T(10, 64); CSA(2);
        if (warp && !wg) mbar_wait(bars + 416 + 8 * warp, 0);
        CSA(3);
        float sc[4][3][4];
#pragma unroll
        for (int h = 0; h < 4; h++) {
            const int jb = 5 * (h >> 1) + 3 * (h & 1), js = 5 * (h >> 1) + 2;
#pragma unroll
            for (int nt = 1; nt < 3; nt++) {
#pragma unroll
                for (int e = 0; e < 4; e++) sc[h][nt][e] = 0.f;
                mma_bf16(sc[h][nt], f[0][jb], f[1][jb], f[0][jb + 1], f[1][jb + 1], f[nt - 1][10 + jb], f[nt - 1][11 + jb]);
                mma_bf16_k8(sc[h][nt], qs[h][0], qs[h][1], f[nt - 1][10 + js]);
            }
        }
        if (warp == 0) halo();
        TSTAMP1(8); CSA(4);
#pragma unroll
        for (int h = 0; h < 4; h++) {
            const int jb = 5 * (h >> 1) + 3 * (h & 1), js = 5 * (h >> 1) + 2;
#pragma unroll
            for (int e = 0; e < 4; e++) sc[h][0][e] = 0.f;
            mma_bf16(sc[h][0], f[0][jb], f[1][jb], f[0][jb + 1], f[1][jb + 1], kp[jb], kp[jb + 1]);
            mma_bf16_k8(sc[h][0], qs[h][0], qs[h][1], kp[js]);
        }
        TSTAMP1T(3, 64);
        float p[4][4], sum[4][2];
        uint32_t lg[4][2], mx[4];
        const float rl[4] = {rk[0] * ra, rk[1] * ra, rk[2] * rb, rk[3] * rb};
        auto max2 = [](uint32_t a, uint32_t b) { uint32_t r; asm("max.bf16x2 %0, %1, %2;" : "=r"(r) : "r"(a), "r"(b)); return r; };
#pragma unroll
        for (int h = 0; h < 4; h++) {
            lg[h][0] = pack2((up0 ? sc[h][0][0] : sc[h][1][0]) * rl[0], (up0 ? sc[h][1][2] : sc[h][2][2]) * rl[2]);
            lg[h][1] = pack2((up1 ? sc[h][0][1] : sc[h][1][1]) * rl[1], (up1 ? sc[h][1][3] : sc[h][2][3]) * rl[3]);
            if (edge) {
                if (up0) lg[h][0] = __byte_perm(lg[h][0], 0xce6eu, 0x3254);
                if (up1) lg[h][1] = __byte_perm(lg[h][1], 0xce6eu, 0x3254);
            }
            mx[h] = max2(lg[h][0], lg[h][1]);
        }
#pragma unroll
        for (int o = 1; o <= 2; o <<= 1)
#pragma unroll
            for (int h = 0; h < 4; h++) mx[h] = max2(mx[h], __shfl_xor_sync(~0u, mx[h], o));
#pragma unroll
        for (int h = 0; h < 4; h++)
#pragma unroll
            for (int r = 0; r < 2; r++) {
                const float m = __uint_as_float(r ? mx[h] & 0xffff0000u : mx[h] << 16);
#pragma unroll
                for (int e = 0; e < 2; e++)
                    asm("ex2.approx.ftz.f32 %0, %1;" : "=f"(p[h][2 * r + e]) : "f"((__uint_as_float(r ? lg[h][e] & 0xffff0000u : lg[h][e] << 16) - m) * 1.4426950408889634f));
                sum[h][r] = p[h][2 * r] + p[h][2 * r + 1];
            }
#pragma unroll
        for (int o = 1; o <= 2; o <<= 1)
#pragma unroll
            for (int h = 0; h < 4; h++)
#pragma unroll
                for (int r = 0; r < 2; r++) sum[h][r] += __shfl_xor_sync(~0u, sum[h][r], o);
        TSTAMP1T(5, 64); CSA(5);
        const uint32_t mu = (up0 ? 0xffffu : 0u) | (up1 ? 0xffff0000u : 0u);
        uint32_t ob[10][2];
#pragma unroll
        for (int P = 0; P < 2; P++) {
            float os[2][4];
#pragma unroll
            for (int e = 0; e < 2; e++) {
                const int h = 2 * P + e;
                const float i0 = rcp_apx(sum[h][0]), i1 = rcp_apx(sum[h][1]);
                const uint32_t w0 = pack2(p[h][0] * rk[0] * i0, p[h][1] * rk[1] * i0), w1 = pack2(p[h][2] * rk[2] * i1, p[h][3] * rk[3] * i1);
#pragma unroll
                for (int dt = 0; dt < 3; dt++) {
                    const int j = 5 * P + (dt < 2 ? 3 * e + dt : 2);
                    float o[4] = {0.f, 0.f, 0.f, 0.f};
                    mma_bf16(o, w0 & ~mu, w1 & mu, 0u, w1 & ~mu, vb[j][0], vb[j][1]);
                    mma_bf16_k8(o, w0 & mu, 0u, vp[j]);
                    if (dt < 2) { ob[j][0] = pack2(o[0], o[1]); ob[j][1] = pack2(o[2], o[3]); }
                    else { os[e][0] = o[0]; os[e][1] = o[1]; os[e][2] = o[2]; os[e][3] = o[3]; }
                }
            }
#pragma unroll
            for (int k = 0; k < 4; k++) os[0][k] = t < 2 ? os[0][k] : os[1][k];
            ob[5 * P + 2][0] = pack2(os[0][0], os[0][1]); ob[5 * P + 2][1] = pack2(os[0][2], os[0][3]);
        }
        const uint32_t sl = sbase + (wg ? A1_SM_A1 : A1_SM_A0);
        const uint32_t o0 = (warp & 3) * 2048 + g * 64 + ((t ^ (g >> 1)) << 4), o1 = 8192 + (warp & 3) * 512 + g * 32 + ((t ^ ((g >> 2) << 1)) << 3);
        mbar_wait(bar_done, 0);
        if (wg == 0) mbar_wait(bar_kvf, 0);
#pragma unroll
        for (int h = 0; h < 2; h++) {
            asm volatile("st.shared.v4.u32 [%0], {%1,%2,%3,%4};" ::"r"(sl + o0 + h * 1024), "r"(ob[0][h]), "r"(ob[1][h]), "r"(ob[2][h]), "r"(ob[3][h]) : "memory");
            asm volatile("st.shared.v4.u32 [%0], {%1,%2,%3,%4};" ::"r"(sl + o0 + h * 1024 + 512), "r"(ob[4][h]), "r"(ob[5][h]), "r"(ob[6][h]), "r"(ob[7][h]) : "memory");
            asm volatile("st.shared.v2.u32 [%0], {%1,%2};" ::"r"(sl + o1 + h * 256), "r"(ob[8][h]), "r"(ob[9][h]) : "memory");
        }
        if (wg && lane == 0) mbar_arrive(bars + 384 + 8 * warp);
        fence_async_smem();
        __syncwarp();
        TSTAMP1T(4, 64); CSA(6);
        TSTAMP1(1);
        TSTAMP2(1);
        const unsigned char* ot = reinterpret_cast<const unsigned char*>(of) + mb * 163840 + wg * 10240;
        if (lane == 0) {
            asm volatile("cp.async.bulk.global.shared::cta.bulk_group [%0], [%1], 2048;" ::"l"(ot + hg * 20480 + (warp & 3) * 2048), "r"(sl + (warp & 3) * 2048) : "memory");
            asm volatile("cp.async.bulk.global.shared::cta.bulk_group [%0], [%1], 512;" ::"l"(ot + hg * 20480 + 8192 + (warp & 3) * 512), "r"(sl + 8192 + (warp & 3) * 512) : "memory");
            asm volatile("cp.async.bulk.commit_group;" ::: "memory");
            if (wg == 0) mbar_arrive(bar_pv);
            asm volatile("cp.async.bulk.wait_group 0;" ::: "memory");
            asm volatile(A1_FRED " [%0], 1;" ::"l"(reinterpret_cast<uint32_t*>(rsum + 2 * SEQ) + (((layer * 16 + mb) * 2 + wg) * 8 + hg) * FSTR) : "memory");
            DBGC(4 + warp);
        }
        TSTAMP4(11); CSA(7);
        float ac2[40];
        const uint64_t db0 = make_desc(sbase, 1024, 256, 3), db1 = make_desc(sbase + 10240, 512, 256, 3), da0 = make_desc(sl, 16, 1024, 2), da1 = make_desc(sl + 8192, 16, 256, 3);
        const uint32_t o7 = wg ? 640 : (A1_SM_W0 - A1_SM_A0) >> 4;
        const uint32_t trow = ((lane & 7) + 8 * (lane >> 4)) * 128 + (((2 * (warp & 3) + ((lane >> 3) & 1)) ^ (lane & 7)) << 4);
        uint32_t xr[10][2];
        mbar_wait(bar_f2 + 64 * wg + 64, 0);
        if (layer == 0) {
#pragma unroll
            for (int j = 0; j < 10; j += 2) ldsm_x4(&xr[j][0], sl + 51200 + (16 * (warp & 3) + (lane & 15)) * 160 + (lane >> 4) * 16 + 16 * j);
        } else {
#pragma unroll
            for (int j = 0; j < 10; j += 2) ldsm_x4_t(&xr[j][0], sl + 51200 + trow + 1024 * j);
        }
        const uint32_t ri = __shfl_sync(~0u, layer * SEQ + (wg * 2 + ((g >> 1) & 1)) * 512 + (mb * 16 + 4 * (warp & 3) + (g >> 2)) * 2 + (g & 1), lane);
        mbar_wait(bar_wo, 0);
        if (wg) mbar_wait(bar_pv, 0);
        if (wg) asm volatile("bar.sync 2, 128;" ::: "memory"); else asm volatile("bar.sync 1, 128;" ::: "memory");
        TSTAMP2(2); CSA(8);
#pragma unroll
        for (int q = 0; q < 8; q++) {
            uint32_t bo = wo_off(0) >> 4;
            if (q) {
                mbar_wait(bar_f2 + 64 * wg + 8 * q, 0);
                asm volatile("ld.shared.u32 %0, [%1];" : "=r"(bo) : "r"(que + 32 * wg + 4 * q) : "memory");
                bo = __shfl_sync(~0u, bo, 0);
                TSTAMP4(q);
                if (q % 3 == 1) CSA(9 + q / 3);
                if (q == 1 && (tid & 127) == 0) DBGC(29 + 8 * wg);
            }
            wgmma_fence();
#pragma unroll
            for (int j = 0; j < 5; j++) wgmma_n80(ac2, (j < 4 ? da0 : da1) + (q == 7 ? o7 : 0u) + (uint64_t)((q < 6 ? q * 640 : 0) + (j & 2) * 16 + (j & 1) * 2), (j < 4 ? db0 : db1) + bo + (uint64_t)((j & 2) * 160 + (j & 1) * 32), j || q);
            wgmma_commit();
            if (q == 0) {
                wgmma_wait<0>();
                if ((tid & 127) == 0) { mbar_arrive(bar_e2 + 16 * wg); mbar_arrive(bar_e2 + 8); }
            }
            if (q == 2 && wg) {
                wgmma_wait<1>();
                if (tid == 128) mbar_arrive(bar_e2 + 24);
            }
        }
        if ((tid & 127) == 0) DBGC(28 + wg * 8 + 7);
        TSTAMP2(3);
        wgmma_wait<0>();
        TSTAMP2(4); CSA(12);
        if (__any_sync(~0u, ac2[0] != ac2[0] || ac2[2] != ac2[2])) {
#pragma unroll
            for (int i = 0; i < 40; i++) ac2[i] = 0.f;
            uint32_t a[20], an[20];
            auto lda = [&](uint32_t (&r)[20], int h) {
#pragma unroll
                for (int u = 0; u < 4; u++)
                    asm volatile("ld.relaxed.gpu.global.v4.u32 {%0,%1,%2,%3}, [%4];" : "=r"(r[4 * u]), "=r"(r[4 * u + 1]), "=r"(r[4 * u + 2]), "=r"(r[4 * u + 3]) : "l"(ot + h * 20480 + o0 + u * 512) : "memory");
#pragma unroll
                for (int u = 0; u < 2; u++)
                    asm volatile("ld.relaxed.gpu.global.v2.u32 {%0,%1}, [%2];" : "=r"(r[16 + 2 * u]), "=r"(r[17 + 2 * u]) : "l"(ot + h * 20480 + o1 + u * 256) : "memory");
            };
            lda(an, 0);
#pragma unroll 5
            for (int k = lane; k < WOB / 16; k += 32)
                reinterpret_cast<uint4*>(stg + (sl - sbase))[k] = __ldcg(reinterpret_cast<const uint4*>(wo + hg * 8 * WOB) + k);
            __syncwarp();
#pragma unroll 1
            for (int h = 0; h < 8; h++) {
#pragma unroll 1
                for (int it = 0; it < SPIN_MAX; it++) {
                    uint32_t m = 0;
#pragma unroll
                    for (int k = 0; k < 20; k += 2) m = __vimax3_u32(m, an[k], an[k + 1]);
                    if (!__any_sync(~0u, m == ~0u)) break;
                    lda(an, h);
                }
#pragma unroll
                for (int k = 0; k < 20; k++) a[k] = an[k];
                lda(an, min(h + 1, 7));
                const uint32_t bp = h == hg ? sl : sbase + wo_off(h + (h < hg));
                const int r0 = 8 * ((lane & 7) >> 1) + 2 * (lane >> 3) + (lane & 1), r2 = 4 * ((lane & 7) >> 1) + 2 * ((lane >> 3) & 1) + (lane & 1);
#pragma unroll
                for (int n = 0; n < 10; n++) {
                    uint32_t b[12];
                    ldsm_x4_t(b, bp + (n >> 1) * 1024 + r0 * 32 + (((n ^ (r0 >> 2)) & 1) << 4));
                    ldsm_x4_t(b + 4, bp + 5120 + (n >> 1) * 1024 + r0 * 32 + (((n ^ (r0 >> 2)) & 1) << 4));
                    ldsm_x4_t(b + 8, bp + 10240 + (n >> 1) * 512 + r2 * 32 + (((n ^ (r2 >> 2)) & 1) << 4));
                    mma_bf16(ac2 + 4 * n, a[0], a[8], a[1], a[9], b[0], b[1]); mma_bf16(ac2 + 4 * n, a[2], a[10], a[3], a[11], b[2], b[3]);
                    mma_bf16(ac2 + 4 * n, a[4], a[12], a[5], a[13], b[4], b[5]); mma_bf16(ac2 + 4 * n, a[6], a[14], a[7], a[15], b[6], b[7]);
                    mma_bf16(ac2 + 4 * n, a[16], a[18], a[17], a[19], b[8], b[9]);
                }
            }
        }
#pragma unroll
        for (int j = 0; j < 10; j++)
#pragma unroll
            for (int hh = 0; hh < 2; hh++) {
                const uint32_t a = pack2(ac2[4 * j + 2 * hh], ac2[4 * j + 2 * hh + 1]);
                const __nv_bfloat162 r = __hadd2_rn(*reinterpret_cast<const __nv_bfloat162*>(&xr[j][hh]), *reinterpret_cast<const __nv_bfloat162*>(&a));
                xr[j][hh] = *reinterpret_cast<const uint32_t*>(&r);
            }
        const uint32_t so = sl + 30720;
#pragma unroll
        for (int j = 0; j < 10; j += 2) stsm_x4_t(so + trow + 1024 * j, xr[j][0], xr[j][1], xr[j + 1][0], xr[j + 1][1]);
        fence_async_smem();
        if (wg) asm volatile("bar.sync 2, 128;" ::: "memory"); else asm volatile("bar.sync 1, 128;" ::: "memory");
        TSTAMP2(5); CSA(13);
        if ((tid & 127) == 0) {
            asm volatile("cp.async.bulk.tensor.2d.global.shared::cta.bulk_group [%0, {%1, %2}], [%3];" ::"l"(&tmX1), "r"(mb * 128 + 64 * wg), "r"(hg * 80), "r"(so) : "memory");
            asm volatile("cp.async.bulk.commit_group;" ::: "memory");
        }
        __syncwarp();
        const float p0 = *(volatile const float*)&rw[g].x, p1 = *(volatile const float*)&rw[g + 8].x;
        float s[3][4] = {};
        const uint32_t pp[2] = {__byte_perm(__float_as_uint(p0), 0, 0x3232), __byte_perm(__float_as_uint(p1), 0, 0x3232)};
#pragma unroll
        for (int j = 0; j < 10; j += 2) {
            const uint32_t d0 = sub2(xr[j][0], pp[0]), d1 = sub2(xr[j][1], pp[1]), d2 = sub2(xr[j + 1][0], pp[0]), d3 = sub2(xr[j + 1][1], pp[1]);
            mma_bf16(s[0], xr[j][0], xr[j][1], xr[j + 1][0], xr[j + 1][1], 0x3f803f80u, 0x3f803f80u);
            mma_bf16(s[1], d0, d1, d2, d3, d0, d2);
            mma_bf16(s[2], d0, d1, d2, d3, d1, d3);
        }
        if (t == (g >> 1)) {
            float2* rp = rsum + ri;
            asm volatile("red.relaxed.gpu.global.add.v2.f32 [%0], {%1, %2};" ::"l"(rp), "f"(fmaf(-80.f, p0, s[0][0])), "f"((g & 1) ? s[1][1] : s[1][0]) : "memory");
            asm volatile("red.relaxed.gpu.global.add.v2.f32 [%0], {%1, %2};" ::"l"(rp + 4), "f"(fmaf(-80.f, p1, s[0][2])), "f"((g & 1) ? s[2][3] : s[2][2]) : "memory");
        }
        asm volatile("cp.async.bulk.wait_group.read 0;" ::: "memory");
        TSTAMP2(6); CSA(14); CSA_END;
        if (tid == 0) DBGC(63);
        if (tid == 128) DBGC(28);
        if (tid == 0) DBGCAL(2);
        GSTAMP(g_tim1, 14);
        SPAN(1 + 4 * layer, 3);
    }
}

static int h_nsm;
static void* h_sym[11];
static TileTab h_tab;
static CUtensorMap h_tmX0, h_tmX1, h_tmR0, h_tmR1, h_tmX1st, h_tmOut, h_tmWq, h_tmWo, h_tmWt;
typedef CUresult (*PFN_encodeTiled)(CUtensorMap*, CUtensorMapDataType, cuuint32_t, void*, const cuuint64_t*, const cuuint64_t*,
                                    const cuuint32_t*, const cuuint32_t*, CUtensorMapInterleave, CUtensorMapSwizzle,
                                    CUtensorMapL2promotion, CUtensorMapFloatOOBfill);
static void make_tmap(CUtensorMap* tm, const void* ptr, uint64_t cols, uint64_t rows, uint32_t bc, uint32_t br, CUtensorMapSwizzle sw, uint64_t pitch = 0, uint64_t hi = 0, uint32_t bh = 2) {
    static PFN_encodeTiled fn = nullptr;
    if (!fn) {
        void* p = nullptr; cudaDriverEntryPointQueryResult qr;
        cudaGetDriverEntryPoint("cuTensorMapEncodeTiled", &p, cudaEnableDefault, &qr);
        fn = (PFN_encodeTiled)p;
    }
    if (br == 0) {
        cuuint64_t dims[5] = {16, 2, rows / 8, 4, cols / 16}; cuuint64_t strides[4] = {cols * 2, cols * 16, cols * 4, 32};
        cuuint32_t box[5] = {16, 2, bc, 4, 5}; cuuint32_t es[5] = {1, 1, 1, 1, 1};
        fn(tm, CU_TENSOR_MAP_DATA_TYPE_BFLOAT16, 5, const_cast<void*>(ptr), dims, strides, box, es, CU_TENSOR_MAP_INTERLEAVE_NONE, sw,
           CU_TENSOR_MAP_L2_PROMOTION_L2_128B, CU_TENSOR_MAP_FLOAT_OOB_FILL_NONE);
        return;
    }
    if (bh == 0) {
        cuuint64_t dims[5] = {64, 64, 2, 16, 10}; cuuint64_t strides[4] = {pitch * 2, hi * 2, cols * 2, rows * 2};
        cuuint32_t box[5] = {64, 64, 2, 1, 1}; cuuint32_t es[5] = {1, 1, 1, 1, 1};
        fn(tm, CU_TENSOR_MAP_DATA_TYPE_BFLOAT16, 5, const_cast<void*>(ptr), dims, strides, box, es, CU_TENSOR_MAP_INTERLEAVE_NONE, sw,
           CU_TENSOR_MAP_L2_PROMOTION_L2_128B, CU_TENSOR_MAP_FLOAT_OOB_FILL_NONE);
        return;
    }
    if (hi) {
        cuuint64_t dims[3] = {cols, rows, hi == 64 ? 32u : hi == 16 ? 120u : 2u}; cuuint64_t strides[2] = {pitch * 2, hi * 2};
        cuuint32_t box[3] = {bc, br, bh}; cuuint32_t es[3] = {1, 1, 1};
        fn(tm, CU_TENSOR_MAP_DATA_TYPE_BFLOAT16, 3, const_cast<void*>(ptr), dims, strides, box, es, CU_TENSOR_MAP_INTERLEAVE_NONE, sw,
           CU_TENSOR_MAP_L2_PROMOTION_L2_128B, CU_TENSOR_MAP_FLOAT_OOB_FILL_NONE);
        return;
    }
    cuuint64_t dims[2] = {cols, rows}; cuuint64_t strides[1] = {(pitch ? pitch : cols) * 2};
    cuuint32_t box[2] = {bc, br}; cuuint32_t es[2] = {1, 1};
    fn(tm, CU_TENSOR_MAP_DATA_TYPE_BFLOAT16, 2, const_cast<void*>(ptr), dims, strides, box, es, CU_TENSOR_MAP_INTERLEAVE_NONE, sw,
       CU_TENSOR_MAP_L2_PROMOTION_L2_128B, CU_TENSOR_MAP_FLOAT_OOB_FILL_NONE);
}
template <typename... Args>
static void launch_pdl(void (*kern)(Args...), int grid, int block, int smem, Args... args) {
    cudaLaunchConfig_t cfg = {};
    cfg.gridDim = dim3(grid); cfg.blockDim = dim3(block); cfg.dynamicSmemBytes = smem; cfg.stream = cudaStreamPerThread;
    cudaLaunchAttribute at[1];
    at[0].id = cudaLaunchAttributeProgrammaticStreamSerialization; at[0].val.programmaticStreamSerializationAllowed = 1;
    cfg.attrs = at; cfg.numAttrs = 1;
    cudaLaunchKernelEx(&cfg, kern, args...);
}
static void launch_stage(int k, void* const* d_in, void* d_out) {
    const KgIn kg = {(const bf16*)d_in[4], (const bf16*)d_in[5], (const bf16*)d_in[6], (const bf16*)d_in[7], (const bf16*)d_in[8], (const bf16*)d_in[9], (const bf16*)d_in[0], (const bf16*)d_in[1], (const bf16*)d_in[2],
                      (uint4*)h_sym[0], (uint4*)h_sym[1], (uint4*)h_sym[2], (uint4*)h_sym[3], (uint4*)h_sym[4], (float*)h_sym[5]};
    switch (k) {
        case 0: kgen_kernel<<<128, 512, KG_SMEM, cudaStreamPerThread>>>(kg, h_tmWq, h_tmWo, h_tmWt); break;
        case 1: launch_pdl(a1_kernel, h_nsm, A1_THREADS, A1_SMEM, 0, (const bf16*)d_in[0], (const unsigned char*)h_sym[1], (const unsigned char*)h_sym[2], (float2*)h_sym[4], (uint4*)h_sym[6], h_tmX0, h_tmR0, h_tmX1st, h_tab); break;
        case 3: launch_pdl(conv_kernel, DM / CV_CPB, CV_THREADS, CV_SMEM, 0, (const uint4*)h_sym[7], (const float4*)h_sym[4], (const bf16*)h_sym[8], (bf16*)h_sym[9], (const uint4*)h_sym[0], h_tmOut); break;
        case 5: launch_pdl(a1_kernel, h_nsm, A1_THREADS, A1_SMEM, 1, (const bf16*)d_in[0], (const unsigned char*)h_sym[1], (const unsigned char*)h_sym[2], (float2*)h_sym[4], (uint4*)h_sym[6], h_tmX1, h_tmR1, h_tmX1st, h_tab); break;
        case 7: launch_pdl(conv_kernel, DM / CV_CPB, CV_THREADS, CV_SMEM, 1, (const uint4*)h_sym[7] + SEQ / 8, (const float4*)h_sym[4] + SEQ / 2, (const bf16*)h_sym[8], (bf16*)h_sym[10], (const uint4*)h_sym[0], h_tmOut); break;
        default: break;
    }
}
static int n_stage_kernels() { return 9; }
static const char* stage_name(int k) { const char* n[] = {"kgen", "a1", "a2", "conv", "tr", "a1", "a2", "conv", "tr"}; return n[k]; }

extern "C" void kernel_launch(void* const* d_in, const int* in_sizes, int n_in, void* d_out, int out_size) {
    (void)in_sizes; (void)n_in; (void)out_size;
    static const void *p_in = nullptr, *p_w1 = nullptr, *p_w2 = nullptr, *p_out = nullptr;
    if (p_in != d_in[0] || p_w1 != d_in[1] || p_w2 != d_in[2] || p_out != d_out) {
        cudaFuncSetAttribute(conv_kernel, cudaFuncAttributeMaxDynamicSharedMemorySize, CV_SMEM);
        cudaFuncSetAttribute(kgen_kernel, cudaFuncAttributeMaxDynamicSharedMemorySize, KG_SMEM);
        cudaFuncSetAttribute(a1_kernel, cudaFuncAttributeMaxDynamicSharedMemorySize, A1_SMEM);
        int dev; cudaGetDevice(&dev); cudaDeviceGetAttribute(&h_nsm, cudaDevAttrMultiProcessorCount, dev);
        if (h_nsm != 132) h_nsm = 128;
        h_tab.ns = h_nsm == 132 ? 132 : ~0u;
        for (int i = 0; i < 264; i++) {
            const int h = (i - 64) >> 1;
            const int t = i >= 132 ? i - 132 : i < 64 ? ((i >> 1) & 7) * 16 + (i >> 4) * 2 + (i & 1) : i < 120 ? (1 + h % 7) * 16 + 8 + (h / 7) * 2 + (i & 1) : i < 124 ? 128 : i - 116;
            const int hg = (4 * (t >> 6) + (t & 3)) & 7;
            h_tab.e[i] = {(unsigned char)((t >> 2) & 15), (unsigned char)hg, (unsigned char)(5 * (hg >> 2)), (unsigned char)t, (uint32_t)(hg * 10 * WQ_STAGE)};
        }
        cudaGetSymbolAddress(&h_sym[0], g_tap); cudaGetSymbolAddress(&h_sym[1], g_wq); cudaGetSymbolAddress(&h_sym[2], g_wo);
        cudaGetSymbolAddress(&h_sym[3], g_halo); cudaGetSymbolAddress(&h_sym[4], g_sum); cudaGetSymbolAddress(&h_sym[5], g_csp); cudaGetSymbolAddress(&h_sym[6], g_of);
        cudaGetSymbolAddress(&h_sym[7], g_piv); cudaGetSymbolAddress(&h_sym[8], g_x1T); cudaGetSymbolAddress(&h_sym[9], g_xcT); cudaGetSymbolAddress(&h_sym[10], g_yT);
        void *px1, *px2;
        cudaGetSymbolAddress(&px1, g_x1T); cudaGetSymbolAddress(&px2, g_xcT);
        make_tmap(&h_tmX0, d_in[0], 128 * 640, 64, 64, 64, CU_TENSOR_MAP_SWIZZLE_128B, 1280, 640, 0);
        make_tmap(&h_tmX1, px2, 128, 64 * XCP, 64, 64, CU_TENSOR_MAP_SWIZZLE_128B, XCP, 64, 0);
        make_tmap(&h_tmR0, d_in[0], 640, 1024, 80, 64, CU_TENSOR_MAP_SWIZZLE_NONE, 1280, 640, 1);
        make_tmap(&h_tmR1, px2, 64, 640, 64, 80, CU_TENSOR_MAP_SWIZZLE_128B, XCP, 64, 1);
        make_tmap(&h_tmX1st, px1, 2048, 640, 64, 80, CU_TENSOR_MAP_SWIZZLE_128B, XCP);
        make_tmap(&h_tmWq, d_in[1], 16, 640, 16, 32, CU_TENSOR_MAP_SWIZZLE_32B, 1920, 16, 5);
        make_tmap(&h_tmWo, d_in[2], 640, 640, 4, 0, CU_TENSOR_MAP_SWIZZLE_32B);
        make_tmap(&h_tmWt, d_in[2], 640, 640, 2, 0, CU_TENSOR_MAP_SWIZZLE_32B);
        make_tmap(&h_tmOut, d_out, 640, 1024, 80, 8, CU_TENSOR_MAP_SWIZZLE_NONE, 1280, 640, 1);
        p_in = d_in[0]; p_w1 = d_in[1]; p_w2 = d_in[2]; p_out = d_out;
    }
    for (int k = 0; k < n_stage_kernels(); k++) launch_stage(k, d_in, d_out);
}
```

```cpp
#include <cuda_runtime.h>
#include <cuda_bf16.h>
#include <stdint.h>
#include <cuda.h>

typedef __nv_bfloat16 bf16;

constexpr int SEQ = 2048;
constexpr int DM = 640;
constexpr int NMODE = 192;

__device__ __forceinline__ float bf2f(bf16 v) { return __bfloat162float(v); }
__device__ __forceinline__ float rbf(float v) {
    uint32_t r;
    asm("cvt.rn.bf16x2.f32 %0, %1, %2;" : "=r"(r) : "f"(v), "f"(0.f));
    return __uint_as_float(r);
}
__device__ __forceinline__ uint32_t pack2(float lo, float hi) {
    __nv_bfloat162 t = __floats2bfloat162_rn(lo, hi);
    return *reinterpret_cast<uint32_t*>(&t);
}
__device__ __forceinline__ void pdl_sync() {
    asm volatile("griddepcontrol.wait;" ::: "memory");
    asm volatile("griddepcontrol.launch_dependents;" ::: "memory");
}
__device__ __forceinline__ float sqrt_apx(float v) { float r; asm("sqrt.approx.ftz.f32 %0, %1;" : "=f"(r) : "f"(v)); return r; }
__device__ __forceinline__ float rcp_apx(float v) { float r; asm("rcp.approx.ftz.f32 %0, %1;" : "=f"(r) : "f"(v)); return r; }
__device__ __forceinline__ uint32_t smem_u32(const void* p) { return (uint32_t)__cvta_generic_to_shared(p); }

constexpr int TAPB = 2 * 152 * 8;
__device__ __align__(128) uint4 g_tap[DM * 128];
#define XPAD 64
constexpr int XCP = SEQ + XPAD;
__device__ __align__(128) bf16 g_x1T[DM * XCP];
__device__ __align__(128) bf16 g_xcT[DM * XCP];
__device__ __align__(128) uint4 g_of[128 * 1280];
constexpr int WQ_STAGE = 240 * 128, WOB = 80 * 160;
__device__ __align__(128) uint4 g_wq[8 * 10 * WQ_STAGE / 16];
__device__ __align__(128) uint4 g_wo[64 * WOB / 16];
__device__ __align__(16) float g_csp[10 * 1920];
#define FSTR 32
__device__ __align__(128) float2 g_sum[2 * SEQ + 256 * FSTR];
__device__ __align__(16) bf16 g_piv[2 * SEQ];
__device__ __align__(128) bf16 g_yT[DM * XCP];
__device__ uint32_t g_epoch;
__device__ __align__(16) unsigned long long g_rstat[SEQ];
__device__ __align__(128) uint4 g_halo[640 * 148];
__device__ __forceinline__ unsigned long long tagw(uint32_t payload, uint32_t tag) { return ((unsigned long long)tag << 32) | payload; }
__device__ __forceinline__ ulonglong2 ld_tag2(const ulonglong2* p) {
    ulonglong2 v;
    asm volatile("ld.relaxed.gpu.global.v2.u64 {%0, %1}, [%2];" : "=l"(v.x), "=l"(v.y) : "l"(p) : "memory");
    return v;
}
__device__ __forceinline__ bool tag_ok(ulonglong2 v, uint32_t tag) { return (uint32_t)(v.x >> 32) == tag && (uint32_t)(v.y >> 32) == tag; }
__device__ __forceinline__ uint32_t ld_epoch() { uint32_t v; asm volatile("ld.relaxed.gpu.global.u32 %0, [%1];" : "=r"(v) : "l"(&g_epoch) : "memory"); return v + 1; }
constexpr int SPIN_MAX = 1 << 20;
__device__ uint32_t g_started[4];
__device__ __forceinline__ void sm_started(int slot) { asm volatile("red.relaxed.gpu.global.add.u32 [%0], 1;" ::"l"(g_started + slot) : "memory"); }
__device__ __noinline__ void sm_idle(int slot) {
    if (threadIdx.x) return;
    sm_started(slot);
    const uint32_t want = ld_epoch() * gridDim.x;
    pdl_sync();
#pragma unroll 1
    for (int it = 0; it < SPIN_MAX; it++) {
        uint32_t v;
        asm volatile("ld.relaxed.gpu.global.u32 %0, [%1];" : "=r"(v) : "l"(g_started + slot) : "memory");
        if ((int)(v - want) >= 0) break;
        __nanosleep(100);
    }
}
struct TileTab { uint32_t ns, pad; struct { unsigned char mb, hg, kb0, tile; uint32_t woff; } __align__(8) e[264]; };
__device__ __forceinline__ bool elect() {
    uint32_t p;
    asm volatile("{\n.reg .pred p;\nelect.sync _|p, 0xffffffff;\nselp.b32 %0, 1, 0, p;\n}" : "=r"(p));
    return p;
}
#define DBG_SYMS
#define TSTAMP(i)
#define TSTAMP1(i)
#define TSTAMP1T(i, t)
#define TSTAMP1X(i, t)
#define SPAN(k, i)
#define GSTAMP(arr, i)
#define TSTAMP2(i)
#define TSTAMP3(i)
#define TSTAMP4(i)
#define TSTAMPK(i, t)
#define TSTAMPC(i)
#define DBGC(i)
#define DBGV(i, v)
#define DBGCAL(i)

#define CSA(i)
#define CSA_END
#define CST(i)
#define CST_END
#define CST_EXTRA 0
__device__ __forceinline__ void mma_bf16(float* d, uint32_t a0, uint32_t a1, uint32_t a2, uint32_t a3, uint32_t b0, uint32_t b1) {
    asm volatile("mma.sync.aligned.m16n8k16.row.col.f32.bf16.bf16.f32 {%0,%1,%2,%3}, {%4,%5,%6,%7}, {%8,%9}, {%0,%1,%2,%3};"
                 : "+f"(d[0]), "+f"(d[1]), "+f"(d[2]), "+f"(d[3]) : "r"(a0), "r"(a1), "r"(a2), "r"(a3), "r"(b0), "r"(b1));
}
__device__ __forceinline__ void mma_bf16_k8(float* d, uint32_t a0, uint32_t a1, uint32_t b0) {
    asm volatile("mma.sync.aligned.m16n8k8.row.col.f32.bf16.bf16.f32 {%0,%1,%2,%3}, {%4,%5}, {%6}, {%0,%1,%2,%3};"
                 : "+f"(d[0]), "+f"(d[1]), "+f"(d[2]), "+f"(d[3]) : "r"(a0), "r"(a1), "r"(b0));
}
__device__ __forceinline__ void ldsm_x4(uint32_t* r, uint32_t addr) {
    asm volatile("ldmatrix.sync.aligned.m8n8.x4.shared.b16 {%0,%1,%2,%3}, [%4];"
                 : "=r"(r[0]), "=r"(r[1]), "=r"(r[2]), "=r"(r[3]) : "r"(addr));
}

__device__ __forceinline__ void ldsm_x4_t(uint32_t* r, uint32_t addr) {
    asm volatile("ldmatrix.sync.aligned.m8n8.x4.trans.shared.b16 {%0,%1,%2,%3}, [%4];"
                 : "=r"(r[0]), "=r"(r[1]), "=r"(r[2]), "=r"(r[3]) : "r"(addr));
}
__device__ __forceinline__ void mbar_init(uint32_t bar, int count) { asm volatile("mbarrier.init.shared::cta.b64 [%0], %1;" ::"r"(bar), "r"(count)); }
__device__ __forceinline__ void mbar_arrive(uint32_t bar) { asm volatile("mbarrier.arrive.shared::cta.b64 _, [%0];" ::"r"(bar) : "memory"); }
__device__ __forceinline__ void mbar_wait(uint32_t bar, uint32_t parity) {
    asm volatile("{\n.reg .pred p;\nWAIT_LOOP:\n"
                 "mbarrier.try_wait.parity.shared::cta.b64 p, [%0], %1;\n"
                 "@p bra.uni WAIT_DONE;\nbra.uni WAIT_LOOP;\nWAIT_DONE:\n}" ::"r"(bar), "r"(parity) : "memory");
}

__device__ __forceinline__ void mbar_expect_tx(uint32_t bar, uint32_t bytes) {
    asm volatile("mbarrier.arrive.expect_tx.shared::cta.b64 _, [%0], %1;" ::"r"(bar), "r"(bytes) : "memory");
}
__device__ __forceinline__ void tma_load_2d(uint32_t dst, const void* tmap, int c0, int c1, uint32_t bar) {
    asm volatile("cp.async.bulk.tensor.2d.shared::cluster.global.mbarrier::complete_tx::bytes [%0], [%1, {%3, %4}], [%2];"
                 ::"r"(dst), "l"(tmap), "r"(bar), "r"(c0), "r"(c1) : "memory");
}
__device__ __forceinline__ void tma_load_3d(uint32_t dst, const void* tmap, int c0, int c1, int c2, uint32_t bar) {
    asm volatile("cp.async.bulk.tensor.3d.shared::cluster.global.mbarrier::complete_tx::bytes [%0], [%1, {%3, %4, %5}], [%2];"
                 ::"r"(dst), "l"(tmap), "r"(bar), "r"(c0), "r"(c1), "r"(c2) : "memory");
}
__device__ __forceinline__ void fence_async_smem() { asm volatile("fence.proxy.async.shared::cta;" ::: "memory"); }
__device__ __forceinline__ void bulk_load(uint32_t dst, const void* src, uint32_t bytes, uint32_t bar) {
    asm volatile("cp.async.bulk.shared::cluster.global.mbarrier::complete_tx::bytes [%0], [%1], %2, [%3];"
                 ::"r"(dst), "l"(src), "r"(bytes), "r"(bar) : "memory");
}
__device__ __forceinline__ void stsm_x4(uint32_t addr, uint32_t r0, uint32_t r1, uint32_t r2, uint32_t r3) {
    asm volatile("stmatrix.sync.aligned.m8n8.x4.shared.b16 [%0], {%1,%2,%3,%4};" ::"r"(addr), "r"(r0), "r"(r1), "r"(r2), "r"(r3) : "memory");
}
__device__ __forceinline__ void stsm_x4_t(uint32_t addr, uint32_t r0, uint32_t r1, uint32_t r2, uint32_t r3) {
    asm volatile("stmatrix.sync.aligned.m8n8.x4.trans.shared.b16 [%0], {%1,%2,%3,%4};" ::"r"(addr), "r"(r0), "r"(r1), "r"(r2), "r"(r3) : "memory");
}
__device__ __forceinline__ void prefetch_tmap(const void* tmap) { asm volatile("prefetch.tensormap [%0];" ::"l"(tmap) : "memory"); }

__device__ __forceinline__ float2 cexp_at(float wr2, float wi, float p) {
    float er;
    asm("ex2.approx.ftz.f32 %0, %1;" : "=f"(er) : "f"(wr2 * p));
    float th = wi * p;
    const float k = rintf(th * 0.15915494309189535f);
    th = fmaf(k, -6.2831854820251465f, th);
    th = fmaf(k, 1.7484555314695172e-7f, th);
    return make_float2(er * __cosf(th), er * __sinf(th));
}
__device__ __forceinline__ float2 cmul(float2 a, float2 b) {
    return make_float2(fmaf(a.x, b.x, -a.y * b.y), fmaf(a.x, b.y, a.y * b.x));
}
__device__ __forceinline__ float2 csqr(float2 a) { return make_float2(fmaf(a.x, a.x, -a.y * a.y), (a.x + a.x) * a.y); }
__device__ __forceinline__ uint32_t packh(float2 v) {
    uint32_t r;
    asm("cvt.rn.f16x2.f32 %0, %1, %2;" : "=r"(r) : "f"(v.y), "f"(v.x));
    return r;
}
__device__ __forceinline__ void mma_f16(float* d, uint32_t a0, uint32_t a1, uint32_t a2, uint32_t a3, uint32_t b0, uint32_t b1) {
    asm volatile("mma.sync.aligned.m16n8k16.row.col.f32.f16.f16.f32 {%0,%1,%2,%3}, {%4,%5,%6,%7}, {%8,%9}, {%0,%1,%2,%3};"
                 : "+f"(d[0]), "+f"(d[1]), "+f"(d[2]), "+f"(d[3]) : "r"(a0), "r"(a1), "r"(a2), "r"(a3), "r"(b0), "r"(b1));
}

struct KgIn { const bf16 *logA, *Aim, *Cre, *Cim, *logdt, *dsk, *x, *wqkv, *wo; uint4 *tap, *wq, *wop, *halo, *sum; float* csp; };
constexpr int KG_THREADS = NMODE / 2;

constexpr int KG_BUF = 15 * 12288, KG_BAR = KG_BUF + 6 * 5120, KG_SMEM = KG_BAR + 64;
__global__ void __launch_bounds__(512, 1) kgen_kernel(const KgIn in, const __grid_constant__ CUtensorMap tmWq, const __grid_constant__ CUtensorMap tmWo,
                                                        const __grid_constant__ CUtensorMap tmWt) {
    extern __shared__ __align__(1024) uint4 tabs[];
#define KG_ROT 0
    const int lane = threadIdx.x & 31, w16 = (__shfl_sync(~0u, threadIdx.x >> 5, 0) + KG_ROT) & 15, grp = w16 / 3, warp = w16 - 3 * grp;
    const int d = blockIdx.x * 5 + grp, tid = warp * 32 + lane;
    uint4* tab = tabs + grp * (3 * 768);
    SPAN(0, 0); SPAN(0, 1);
    TSTAMPK(0, 0);
    asm volatile("griddepcontrol.launch_dependents;" ::: "memory");
    if (w16 == 15) {
        const uint32_t b0 = smem_u32(tab), wbar = b0 + 6 * 5120;
        const int blk = blockIdx.x, nq = blk < 112 ? 4 : 2, nj = nq + (blk < 64 ? 1 : 2);
        auto fetch = [&](int i) {
            const uint32_t dst = b0 + i * 5120, bar = wbar + 8 * i;
            if (i < nq) {
                const int p = blk + 64 * (i & 2), kb = p / 24;
                mbar_expect_tx(bar, 5120);
                tma_load_3d(dst, &tmWq, 0, kb * 64 + (i & 1) * 32, (p - 24 * kb) * 5, bar);
            } else if (i < nj) {
                const int o = i == nq ? blk : 255 - blk;
                mbar_expect_tx(bar, o < 128 ? 5120 : 2560);
                asm volatile("cp.async.bulk.tensor.5d.shared::cluster.global.mbarrier::complete_tx::bytes [%0], [%1, {%3, %3, %4, %3, %5}], [%2];"
                             ::"r"(dst), "l"(o < 128 ? &tmWo : &tmWt), "r"(bar), "r"(0), "r"((o & 7) * 10 + (o >> 6) * 4), "r"(((o >> 3) & 7) * 5) : "memory");
            }
        };
        const bool one = elect();
        if (one) {
#pragma unroll
            for (int i = 0; i < 6; i++) mbar_init(wbar + 8 * i, 1);
            asm volatile("fence.mbarrier_init.release.cluster;" ::: "memory");
#pragma unroll
            for (int i = 0; i < 6; i++) fetch(i);
        }
        __syncwarp();
#pragma unroll
        for (int i = 1; i <= 5; i++) asm volatile("bar.arrive %0, 128;" ::"r"(i) : "memory");
        if (one) {
#pragma unroll 1
            for (int i = 0; i < nj; i++) {
                const int p = blk + 64 * (i & 2), kb = p / 24, hg = p & 7, sec = (p - 24 * kb) >> 3, o = i == nq ? blk : 255 - blk, cg = (o >> 3) & 7, hb = o & 7;
                const unsigned char* dst = i < nq ? reinterpret_cast<unsigned char*>(in.wq) + (hg * 10 + (hg < 4 ? kb : kb < 5 ? kb + 5 : kb - 5)) * WQ_STAGE + ((i & 1) * 3 + sec) * 5120
                                                  : reinterpret_cast<unsigned char*>(in.wop) + (cg * 8 + (hb == cg ? 0 : hb + (hb < cg))) * WOB + (o >> 6) * 5120;
                mbar_wait(wbar + 8 * i, 0);
                if (i == 0) TSTAMPK(2, (15 - KG_ROT) * 32);
                if (i == 3) TSTAMPK(5, (15 - KG_ROT) * 32);
                asm volatile("cp.async.bulk.global.shared::cta.bulk_group [%0], [%1], %2;" ::"l"(dst), "r"(b0 + i * 5120), "r"(i < nq || o < 128 ? 5120 : 2560) : "memory");
            }
            asm volatile("cp.async.bulk.commit_group;" ::: "memory");
            asm volatile("cp.async.bulk.wait_group.read 0;" ::: "memory");
        }
        TSTAMPK(11, (15 - KG_ROT) * 32);
        return;
    }
    const bf16 pdt = in.logdt[d], pdsk = in.dsk[d];
    const uint32_t pla = reinterpret_cast<const uint32_t*>(in.logA)[d * KG_THREADS + tid], pai = reinterpret_cast<const uint32_t*>(in.Aim)[d * KG_THREADS + tid];
    const uint32_t pcr = reinterpret_cast<const uint32_t*>(in.Cre)[d * KG_THREADS + tid], pci = reinterpret_cast<const uint32_t*>(in.Cim)[d * KG_THREADS + tid];
    const bf16* pfq = tid < 30 ? in.wqkv + (size_t)(d * 30 + tid) * 64 : tid < 40 ? in.wo + (size_t)(d * 10 + tid - 30) * 64 : in.x + (size_t)(d * 32 + tid - 40) * 64;
#define KG_PF 0
    if (tid < (KG_PF == 3 ? 0 : KG_PF ? 40 : 72)) asm volatile("prefetch.global.L2 [%0];" ::"l"(pfq));
    asm volatile("st.global.v4.u32 [%0], {%1,%1,%1,%1};" ::"l"(in.halo + d * 148 + tid), "r"(~0u));
    if (tid < 52) asm volatile("st.global.v4.u32 [%0], {%1,%1,%1,%1};" ::"l"(in.halo + d * 148 + 96 + tid), "r"(~0u));
    else if (w16 == 2) {
        if (lane < 16) in.sum[blockIdx.x * 16 + lane] = make_uint4(0, 0, 0, 0);
        else if (lane < 20) reinterpret_cast<uint32_t*>(in.sum + 2048)[(blockIdx.x * 4 + lane - 16) * FSTR] = 0;
    }
    const uint32_t tw = smem_u32(tab) + warp * 12288;
    const int g = lane >> 2, t = lane & 3;
    const uint32_t sta = tw + lane * 128 + ((2 * (lane & 3) + ((lane >> 2) & 1)) << 4);
    const uint32_t lda = tw + t * 128 + ((g ^ (2 * t)) << 4);
    const uint32_t stb = tw + lane * 8, ldb = tw + g * 512 + (g & 3) * 32 + t * 8;
    auto sts4 = [&](int e, int off, uint32_t a, uint32_t b, uint32_t c, uint32_t dd) {
        asm volatile("st.shared.v4.u32 [%0], {%1,%2,%3,%4};" ::"r"((sta ^ (e << 4)) + off), "r"(a), "r"(b), "r"(c), "r"(dd) : "memory");
    };
    auto lds4 = [&](int sp, int off, uint32_t* r) {
        asm volatile("ld.shared.v4.u32 {%0,%1,%2,%3}, [%4];" : "=r"(r[0]), "=r"(r[1]), "=r"(r[2]), "=r"(r[3]) : "r"((lda ^ ((sp & 1) << 4)) + sp * 512 + off) : "memory");
    };
    const float dt = rbf(expf(bf2f(pdt)));
    float2 C[2], y1[2], z8[2], y128[2];
    float cmax = 0.f;
#pragma unroll
    for (int m = 0; m < 2; m++) {
        const float wr2 = -rbf(expf(__uint_as_float(m ? pla & 0xffff0000u : pla << 16))) * dt * 1.4426950408889634f;
        const float wi = __uint_as_float(m ? pai & 0xffff0000u : pai << 16) * dt;
        C[m] = make_float2(__uint_as_float(m ? pcr & 0xffff0000u : pcr << 16) * dt, -__uint_as_float(m ? pci & 0xffff0000u : pci << 16) * dt);
        cmax = fmaxf(cmax, fmaxf(fabsf(C[m].x), fabsf(C[m].y)));
        y1[m] = cexp_at(wr2, -wi, 1.f); z8[m] = cexp_at(wr2, wi, 8.f); y128[m] = cexp_at(wr2, -wi, 128.f);
    }
    const int ex = min(max((int)(__reduce_max_sync(~0u, __float_as_uint(cmax)) >> 23), 20), 240);
    const float scale = __uint_as_float((uint32_t)(127 + 10 + 127 - ex) << 23), unscale = 2.0f * __uint_as_float((uint32_t)(ex - 10) << 23);
    TSTAMPK(4, 64);
    if (KG_PF >= 2 && tid >= 40 && tid < 72) asm volatile("prefetch.global.L2 [%0];" ::"l"(pfq));
    float k2048 = 0.f;
    float acc[5][4];
#pragma unroll
    for (int j = 0; j < 5; j++)
#pragma unroll
        for (int k = 0; k < 4; k++) acc[j][k] = 0.f;
    uint32_t af[8][4];
    {
        float2 h0[2], h1[2], g0[2], g1[2], g2[2], g2b[2], g3[2], g4[2], y2[2], y4[2];
#pragma unroll
        for (int m = 0; m < 2; m++) {
            h0[m] = make_float2(1.f, 0.f); h1[m] = csqr(csqr(csqr(z8[m])));
            g0[m] = make_float2(C[m].x * scale, C[m].y * scale);
            g1[m] = cmul(g0[m], y128[m]);
            const float2 y256 = csqr(y128[m]), y512 = csqr(y256);
            g2b[m] = g2[m] = cmul(g0[m], y256); g3[m] = cmul(g0[m], y512); g4[m] = cmul(g3[m], y512);
            y2[m] = csqr(y1[m]); y4[m] = csqr(y2[m]);
            const float2 y1024 = csqr(y512);
            k2048 += fmaf(g4[m].x, y1024.x, -g4[m].y * y1024.y);
        }
#pragma unroll
        for (int e = 0; e < 8; e++) {
            sts4(e, 0, packh(h0[0]), packh(h1[0]), packh(h0[1]), packh(h1[1]));
            sts4(e, 4096, packh(g0[0]), packh(g0[1]), packh(g1[0]), packh(g1[1]));
#pragma unroll
            for (int m = 0; m < 2; m++)
                if (e < 7) { h0[m] = e ? cmul(h0[m], z8[m]) : z8[m]; h1[m] = cmul(h1[m], z8[m]); g0[m] = cmul(g0[m], y1[m]); g1[m] = cmul(g1[m], y1[m]); }
            if (e < 5) k2048 += __shfl_xor_sync(~0u, k2048, 1 << e);
        }
        if (KG_PF == 1 && tid >= 40 && tid < 72) asm volatile("prefetch.global.L2 [%0];" ::"l"(pfq));
        __syncwarp();
#pragma unroll
        for (int e = 0; e < 8; e++) {
            uint32_t b[4];
            lds4(e, 0, af[e]); lds4(e, 4096, b);
            sts4(e, 8192, packh(g2[0]), packh(g2[1]), packh((e & 1) ? cmul(g3[0], y4[0]) : g3[0]), packh((e & 1) ? cmul(g3[1], y4[1]) : g3[1]));
            asm volatile("st.shared.v2.u32 [%0], {%1,%2};" ::"r"((stb ^ ((e & 3) << 5)) + e * 512), "r"(packh(g4[0])), "r"(packh(g4[1])) : "memory");
#pragma unroll
            for (int m = 0; m < 2; m++)
                if (e < 7) {
                    g2[m] = e == 3 ? cmul(g2b[m], y128[m]) : cmul(g2[m], y2[m]);
                    if (e & 1) g3[m] = cmul(g3[m], y128[m]);
                    g4[m] = cmul(g4[m], y128[m]);
                }
            mma_f16(acc[0], af[e][0], af[e][1], af[e][2], af[e][3], b[0], b[1]);
            mma_f16(acc[1], af[e][0], af[e][1], af[e][2], af[e][3], b[2], b[3]);
        }
    }
    TSTAMPK(6, 64);
    __syncwarp();
#pragma unroll
    for (int sp = 0; sp < 8; sp++) {
        uint32_t c[4], e0, e1;
        lds4(sp, 8192, c);
        asm volatile("ld.shared.v2.u32 {%0,%1}, [%2];" : "=r"(e0), "=r"(e1) : "r"(ldb ^ (sp << 5)) : "memory");
        mma_f16(acc[2], af[sp][0], af[sp][1], af[sp][2], af[sp][3], c[0], c[1]);
        mma_f16(acc[3], af[sp][0], af[sp][1], af[sp][2], af[sp][3], c[2], c[3]);
        mma_f16(acc[4], af[sp][0], af[sp][1], af[sp][2], af[sp][3], e0, e1);
    }
    {
        float* Pp = reinterpret_cast<float*>(tab + warp * 768);
        auto sw = [](int i) { return i ^ ((i >> 2) & 24); };
#pragma unroll
        for (int h = 0; h < 2; h++) {
            const int b = g + 8 * h;
            *reinterpret_cast<float2*>(Pp + sw(8 * b + 2 * t)) = make_float2(acc[0][2 * h] * unscale, acc[0][2 * h + 1] * unscale);
            *reinterpret_cast<float2*>(Pp + 128 + sw(8 * b + 2 * t)) = make_float2(acc[1][2 * h] * unscale, acc[1][2 * h + 1] * unscale);
            *reinterpret_cast<float2*>(Pp + 256 + sw(4 * b + 2 * (t & 1) + 64 * (t >> 1))) = make_float2(acc[2][2 * h] * unscale, acc[2][2 * h + 1] * unscale);
            *reinterpret_cast<float2*>(Pp + 384 + sw(2 * b + 32 * t)) = make_float2(acc[3][2 * h] * unscale, acc[3][2 * h + 1] * unscale);
            Pp[512 + sw(b + 32 * t)] = acc[4][2 * h] * unscale;
            Pp[512 + sw(b + 32 * t + 16)] = acc[4][2 * h + 1] * unscale;
        }
        if (lane == 0) Pp[640] = k2048 * unscale;
    }
    TSTAMPK(7, 64);
    asm volatile("bar.sync %0, 128;" ::"r"(grp + 1) : "memory");
    TSTAMPK(9, 64);
    const float* Kp = reinterpret_cast<const float*>(tab);
    auto ksum = [&](int i) -> float { return (Kp[i] + Kp[3072 + i]) + Kp[6144 + i]; };
    auto ksum4 = [&](int q) -> float4 {
        q ^= (q >> 2) & 6;
        const float4 a = reinterpret_cast<const float4*>(Kp)[q], b = reinterpret_cast<const float4*>(Kp)[768 + q], c = reinterpret_cast<const float4*>(Kp)[1536 + q];
        return make_float4((a.x + b.x) + c.x, (a.y + b.y) + c.y, (a.z + b.z) + c.z, (a.w + b.w) + c.w);
    };
    {
        uint2* E4 = reinterpret_cast<uint2*>(in.tap + d * 128);
        float4 v = ksum4(tid), u = ksum4(96 + min(tid, 64));
        const float cor = rbf(ksum(tid == 95 ? 384 : 512));
        if (tid == 0) v.x += bf2f(pdsk);
        if (tid == 95) v.w -= cor;
        if (tid == 31) u.w -= cor;
        const uint32_t lo = pack2(v.x, v.y), hi = pack2(v.z, v.w);
        if (tid < 64) {
            E4[6 + tid] = make_uint2(lo, hi);
            E4[(tid < 32 ? 159 : 209 - 32) + tid] = make_uint2(pack2(u.x, u.y), pack2(u.z, u.w));
        } else {
            const uint32_t nx = __shfl_down_sync(~0u, lo, 1);
            in.tap[d * 128 + 35 + tid - 64] = make_uint4(__byte_perm(lo, 0, 0x1010), __byte_perm(lo, hi, 0x5432), __byte_perm(hi, 0, 0x1010), __byte_perm(hi, tid == 95 ? 0u : nx, 0x5432));
            if (tid == 64) E4[241] = make_uint2(pack2(u.x, 0.f), 0u);
        }
    }
    TSTAMPK(10, 64);
    if (warp < (blockIdx.x < 112 ? 2 : 1)) {
        const uint32_t sb = smem_u32(tabs);
        mbar_wait(sb + KG_BAR + 16 * warp, 0); mbar_wait(sb + KG_BAR + 16 * warp + 8, 0);
        uint32_t w[4][4];
        float cs[4] = {0.f, 0.f, 0.f, 0.f};
#pragma unroll
        for (int a = 0; a < 4; a++)
            ldsm_x4_t(w[a], sb + KG_BUF + warp * 10240 + grp * 1024 + ((lane >> 4) * 8 + (lane & 7)) * 32 + ((((lane >> 3) ^ (lane >> 2)) & 1) << 4) + (a >> 1) * 5120 + (a & 1) * 512);
#pragma unroll
        for (int a = 0; a < 4; a++) mma_bf16(cs, w[a][0], w[a][1], w[a][2], w[a][3], 0x3f803f80u, 0x3f803f80u);
        if (t < 2) in.csp[(blockIdx.x + 128 * warp) * 80 + grp * 16 + g + 8 * t] = t ? cs[2] : cs[0];
    }
    SPAN(0, 3);
}

#define CV_SLEEP 40
#define CV_D2 3
#define CV_PDH 12
#define CV_PDF 4
#define CV_HAND 7
constexpr int CV_CPB = 5;
constexpr int CV_THREADS = 512;
constexpr int UPADF = 128;
constexpr int ULEN = UPADF + SEQ;
constexpr int XLEN = SEQ + 16;
constexpr int BX_5 = 0, BX_3 = 3264, BX_9 = 6528, BX_7 = 8960, BX_LEN = 11392;
constexpr int CV_SM_U = 0;
constexpr int CV_SM_T = CV_CPB * ULEN * 2;
constexpr int CV_SM_B = CV_SM_T + CV_CPB * TAPB;
constexpr int CV_SM_X = CV_SM_B + CV_CPB * BX_LEN;
constexpr int CV_SM_Y = (CV_SM_X + CV_CPB * XLEN * 2 + 127) & ~127;
constexpr int CV_SM_CNT = CV_SM_Y + CV_CPB * 8192;
constexpr int CV_SM_O = CV_SM_CNT + 128;
constexpr int CV_SMEM = CV_SM_O + 20480 + CST_EXTRA;
static_assert(ULEN % 128 == 0 && CV_SM_B % 128 == 0 && CV_SM_CNT % 128 == 0, "layout");

__device__ __forceinline__ uint32_t sub2(uint32_t x, uint32_t m) {
    const __nv_bfloat162 d = __hsub2(*reinterpret_cast<const __nv_bfloat162*>(&x), *reinterpret_cast<const __nv_bfloat162*>(&m));
    return *reinterpret_cast<const uint32_t*>(&d);
}
__device__ __forceinline__ uint32_t add2(uint32_t x, uint32_t y) {
    const __nv_bfloat162 d = __hadd2_rn(*reinterpret_cast<const __nv_bfloat162*>(&x), *reinterpret_cast<const __nv_bfloat162*>(&y));
    return *reinterpret_cast<const uint32_t*>(&d);
}
__device__ __forceinline__ void wgmma_fence() { asm volatile("wgmma.fence.sync.aligned;" ::: "memory"); }
__device__ __forceinline__ void wgmma_commit() { asm volatile("wgmma.commit_group.sync.aligned;" ::: "memory"); }
template <int N> __device__ __forceinline__ void wgmma_wait() { asm volatile("wgmma.wait_group.sync.aligned %0;" ::"n"(N) : "memory"); }
__device__ __forceinline__ uint64_t make_desc(uint32_t addr, uint32_t lbo, uint32_t sbo, uint32_t mode) {
    return (uint64_t)((addr & 0x3FFFF) >> 4) | ((uint64_t)(lbo >> 4) << 16) | ((uint64_t)(sbo >> 4) << 32) | ((uint64_t)mode << 62);
}
__device__ __forceinline__ void wgmma_rs128(float (&d)[64], uint2 hi, uint2 lo, uint64_t db, int acc) {
    asm volatile("{\n.reg .pred p;\nsetp.ne.b32 p, %69, 0;\nwgmma.mma_async.sync.aligned.m64n128k16.f32.bf16.bf16 {%0,%1,%2,%3,%4,%5,%6,%7,%8,%9,%10,%11,%12,%13,%14,%15,%16,%17,%18,%19,%20,%21,%22,%23,%24,%25,%26,%27,%28,%29,%30,%31,%32,%33,%34,%35,%36,%37,%38,%39,%40,%41,%42,%43,%44,%45,%46,%47,%48,%49,%50,%51,%52,%53,%54,%55,%56,%57,%58,%59,%60,%61,%62,%63}, {%64,%65,%66,%67}, %68, p, 1, 1, 0;\n}"
                 : "+f"(d[0]), "+f"(d[1]), "+f"(d[2]), "+f"(d[3]), "+f"(d[4]), "+f"(d[5]), "+f"(d[6]), "+f"(d[7]), "+f"(d[8]), "+f"(d[9]), "+f"(d[10]), "+f"(d[11]), "+f"(d[12]), "+f"(d[13]), "+f"(d[14]), "+f"(d[15]), "+f"(d[16]), "+f"(d[17]), "+f"(d[18]), "+f"(d[19]), "+f"(d[20]), "+f"(d[21]), "+f"(d[22]), "+f"(d[23]), "+f"(d[24]), "+f"(d[25]), "+f"(d[26]), "+f"(d[27]), "+f"(d[28]), "+f"(d[29]), "+f"(d[30]), "+f"(d[31]), "+f"(d[32]), "+f"(d[33]), "+f"(d[34]), "+f"(d[35]), "+f"(d[36]), "+f"(d[37]), "+f"(d[38]), "+f"(d[39]), "+f"(d[40]), "+f"(d[41]), "+f"(d[42]), "+f"(d[43]), "+f"(d[44]), "+f"(d[45]), "+f"(d[46]), "+f"(d[47]), "+f"(d[48]), "+f"(d[49]), "+f"(d[50]), "+f"(d[51]), "+f"(d[52]), "+f"(d[53]), "+f"(d[54]), "+f"(d[55]), "+f"(d[56]), "+f"(d[57]), "+f"(d[58]), "+f"(d[59]), "+f"(d[60]), "+f"(d[61]), "+f"(d[62]), "+f"(d[63])
                 : "r"(hi.x), "r"(hi.y), "r"(lo.x), "r"(lo.y), "l"(db), "r"(acc));
}
template <int V> struct Int { __device__ constexpr operator int() const { return V; } };
__device__ __forceinline__ void sts4(uint32_t a, const uint32_t* v) { asm volatile("st.shared.v4.u32 [%0], {%1,%2,%3,%4};" ::"r"(a), "r"(v[0]), "r"(v[1]), "r"(v[2]), "r"(v[3]) : "memory"); }
__device__ __forceinline__ uint32_t lds1(uint32_t a) { uint32_t v; asm volatile("ld.shared.u32 %0, [%1];" : "=r"(v) : "r"(a) : "memory"); return v; }
__device__ __forceinline__ uint4 lds4(uint32_t a) { uint4 v; asm volatile("ld.shared.v4.u32 {%0,%1,%2,%3}, [%4];" : "=r"(v.x), "=r"(v.y), "=r"(v.z), "=r"(v.w) : "r"(a) : "memory"); return v; }
__device__ __forceinline__ void cv_store(unsigned char* p, uint4 x, uint4 y) {
    asm volatile("st.relaxed.gpu.global.v2.u32 [%0], {%1,%2};" ::"l"(p), "r"(add2(x.x, __byte_perm(y.x, y.y, 0x5410))), "r"(add2(x.y, __byte_perm(y.z, y.w, 0x5410))) : "memory");
    asm volatile("st.relaxed.gpu.global.v2.u32 [%0], {%1,%2};" ::"l"(p + 128), "r"(add2(x.z, __byte_perm(y.x, y.y, 0x7632))), "r"(add2(x.w, __byte_perm(y.z, y.w, 0x7632))) : "memory");
}
__device__ __forceinline__ int usw(int ch) { return ch ^ ((ch >> 3) & 1); }
__global__ void __launch_bounds__(CV_THREADS, 1) conv_kernel(int layer, const uint4* __restrict__ piv, const float4* __restrict__ sum, const bf16* __restrict__ x1T,
                                                             bf16* __restrict__ dst, const uint4* __restrict__ tap, const __grid_constant__ CUtensorMap tmOut) {
    extern __shared__ __align__(1024) unsigned char sm[];
    SPAN(3 + 4 * layer, 0);
    bf16* Us = reinterpret_cast<bf16*>(sm + CV_SM_U);
    bf16* Xs = reinterpret_cast<bf16*>(sm + CV_SM_X);
#define CV_IDX int tid; asm volatile("mov.u32 %0, %tid.x;" : "=r"(tid)); const int lane = tid & 31, warp = __shfl_sync(~0u, tid >> 5, 0);
    const int d0 = blockIdx.x * CV_CPB, tile = blockIdx.x; (void)tile;
    const uint32_t cnt = smem_u32(sm + CV_SM_CNT);
    struct Lc { uint32_t a4, a8, uc, ud, y, e4, en, sp, ss; int go; };
    auto lane_consts = [&](int lane, int c) {
        const int mat = lane >> 3, r = lane & 7, g = lane >> 2, ti = lane & 3, e = g - 2 * ti;
        const int j2 = 13 + (r ^ 1) + 8 * (mat >> 1), j3 = j2 + 2, i0 = 8 * (mat & 1);
        const uint32_t sb = smem_u32(sm), oc = sb + usw(16 * (mat >> 1) + 2 * r + (mat & 1)) * 16;
        const Lc l = {sb + CV_SM_B + c * BX_LEN + ((j2 & 1) ? BX_3 + (4 * j2 + i0 + 84) * 2 : BX_5 + (4 * j2 + i0 + 80) * 2),
                      sb + CV_SM_B + c * BX_LEN + ((j3 & 1) ? BX_7 : BX_9) + (8 * j3 + i0 + 136) * 2,
                      oc + CV_SM_U + (c * ULEN + UPADF) * 2, sb + CV_SM_U + (c * ULEN + UPADF) * 2 + usw(16 * mat + 2 * r + 2) * 16, oc + CV_SM_Y + c * 8192,
                      sb + CV_SM_O + 2048 * c + (307 + 2 * g - ti) * 4, sb + CV_SM_T + c * TAPB + (152 + 144 + e) * 8 + 4,
                      e == -5 ? 0x4410u : e == -4 ? 0x1044u : 0x4444u, e == 3 ? 0x4410u : e == 4 ? 0x1044u : 0x4444u,
                      c * XCP * 2 + (lane >> 4) * 256 + (lane & 15) * 8};
        asm volatile("st.shared.u32 [%0], %1;" ::"r"(l.y), "r"(l.a4 ^ l.a8 ^ l.uc ^ l.ud ^ l.e4 ^ l.en ^ l.sp ^ l.ss ^ l.go) : "memory");
        return l;
    };
    unsigned char* const dq = reinterpret_cast<unsigned char*>(dst + (size_t)d0 * XCP);
    auto far = [&](auto T0_, const auto& seq, const Lc& lc, int c, int lane, const uint2 (&f)[20], uint32_t kk) {
        constexpr int T0 = T0_, T1 = T0 + 6, TC = T0 > 7 ? T0 : 7, NS = sizeof(seq) / sizeof(seq[0]), PD = T0 > 7 ? CV_PDH : CV_PDF;
        uint32_t bq[28], yw[4], yz[4], P, S;
        uint4 xv, yv;
        asm("prmt.b32 %0, %1, 0, %2;" : "=r"(P) : "r"(kk), "r"(lc.sp));
        asm("prmt.b32 %0, %1, 0, %2;" : "=r"(S) : "r"(kk), "r"(lc.ss));
#pragma unroll
        for (int k = 0; 2 * k < T1 - TC + 4; k++) ldsm_x4(bq + 4 * k, lc.uc + (TC - 8) * 256 + 512 * k);
#pragma unroll
        for (int k = 0; 4 * k < T1 - TC; k++) ldsm_x4(bq + 20 + 4 * k, lc.ud + (TC - 8) * 256 + 1024 * k);
        CST(3);
        mbar_wait(cnt + 8 * c, 0);
        mbar_wait(cnt + 40, 0);
        CST(4);
        float acc[6][4] = {};
        uint32_t a[PD + 1][4];
#pragma unroll
        for (int i = -PD; i < NS + 3; i++) {
            if (i + PD < NS) ldsm_x4_t(a[(i + PD) % (PD + 1)], seq[i + PD] < 32 ? lc.a4 + (seq[i + PD] - 2) * 128 : lc.a8 + (seq[i + PD] - 34) * 256);
            if (i < 0) continue;
#pragma unroll
            for (int T = T0; T < T1; T++) {
                if (i >= NS) break;
                const int ee = seq[i] < 32 ? 2 * T - 6 - seq[i] : T + 35 - seq[i];
                if (i == 0 && T >= TC) mma_bf16(acc[T - T0], P, 0u, S, P, bq[2 * (T - TC)], bq[2 * (T - TC) + 1]);
                if (i == 1 && T >= TC) mma_bf16_k8(acc[T - T0], 0u, S, bq[20 + T - TC]);
                if (i == (T >= TC ? 2 : 0)) mma_bf16(acc[T - T0], f[19].x, 0u, f[19].y, f[19].x, bq[2 * (T - TC + 4)], bq[2 * (T - TC + 4) + 1]);
                if (seq[i] < 32 ? ee >= 0 && ee <= 9 : ee >= 10) mma_bf16(acc[T - T0], a[i % (PD + 1)][0], a[i % (PD + 1)][1], a[i % (PD + 1)][2], a[i % (PD + 1)][3], f[ee].x, f[ee].y);
            }
#pragma unroll
            for (int k = 0; k < 3; k++) {
                const int o = 256 * T0 + 512 * k;
                auto at = [&](int d) { return i - d >= 0 && i - d < NS && seq[i - d < 0 ? 0 : i - d < NS ? i - d : 0] == 2 * T0 + 4 * k - 4; };
                if (at(CV_D2)) {
                    cv_store(dq + lc.go + o, xv, yv);
                    if (layer > 19 - 2 * k) __trap();
                }
                if (at(-2)) { ldsm_x4_t(yw, lc.y + o); ldsm_x4_t(yz, lc.y + 3584 + o); }
                if (at(1)) {
#pragma unroll
                    for (int q = 0; q < 4; q++) yw[q] = add2(add2(yw[q], yz[q]), pack2(acc[2 * k + (q >> 1)][2 * (q & 1)], acc[2 * k + (q >> 1)][2 * (q & 1) + 1]));
                    stsm_x4_t(lc.y + o, yw[0], yw[1], yw[2], yw[3]);
                    xv = lds4(smem_u32(Xs + c * XLEN) + o + lane * 16);
                    __syncwarp();
                    yv = lds4(smem_u32(sm + CV_SM_Y) + c * 8192 + o + usw(lane) * 16);
                    if (layer > 20 - 2 * k) __trap();
                    if (k == 2) CST(6);
                }
            }
        }
    };
    TSTAMP1X(9, 256);
    if (threadIdx.x >= 256) {
        CV_IDX
        const int t2 = tid - 256, wgu = (warp >> 2) & 1, g = lane >> 2, ti = lane & 3;
        if (t2 == 0) {
            mbar_init(cnt + 48, 1);
            asm volatile("fence.mbarrier_init.release.cluster;" ::: "memory");
            mbar_expect_tx(cnt + 48, CV_CPB * 2048);
            bulk_load(smem_u32(sm + CV_SM_O), tap + d0 * 128, CV_CPB * 2048, cnt + 48);
        } else if (lane == 0) {
            if (warp < 15) mbar_init(cnt + 8 * (warp - 9), warp == 14 ? 8 : 4);
            else if (layer) prefetch_tmap(&tmOut);
        }
        if (t2 < 140) {
            const int k = t2;
            const int off = k < 20 ? CV_SM_B + BX_5 + 8 * k : k < 40 ? CV_SM_B + BX_3 + 8 * (k - 20) : k < 74 ? CV_SM_B + BX_9 + 8 * (k - 40) : k < 108 ? CV_SM_B + BX_7 + 8 * (k - 74) : CV_SM_U + 8 * (k - 108);
            const int str = k < 108 ? BX_LEN : ULEN * 2;
#pragma unroll
            for (int c = 0; c < CV_CPB; c++) *reinterpret_cast<uint2*>(sm + off + c * str) = make_uint2(0, 0);
        }
        fence_async_smem();
        asm volatile("bar.arrive 3, 512;" ::: "memory");
        asm volatile("bar.sync 1, 256;" ::: "memory");
        TSTAMP1X(10, 256);
        asm volatile("setmaxnreg.inc.sync.aligned.u32 168;");
        const int hc = wgu ? warp & 3 : 4;
        const Lc lc = lane_consts(lane, hc);
        const uint32_t* E2[3];
#pragma unroll
        for (int k = 0; k < 3; k++) {
            const int i = min(t2 + 256 * k, 759), h = i / 76;
            E2[k] = reinterpret_cast<const uint32_t*>(sm + CV_SM_O) + 3 + i + (h >> 1) * 360 + (h & 1) * 52;
        }
        mbar_wait(cnt + 48, 0);
        TSTAMP1X(11, 256);
        {
            uint32_t w[3][4];
#pragma unroll
            for (int k = 0; k < 3; k++) { w[k][0] = E2[k][0]; w[k][1] = E2[k][1]; w[k][2] = E2[k][64]; w[k][3] = E2[k][65]; }
#pragma unroll
            for (int k = 0; k < 3; k++)
                *reinterpret_cast<uint4*>(sm + CV_SM_T + min(t2 + 256 * k, 759) * 16) =
                    make_uint4(__byte_perm(w[k][1], w[k][0], 0x7610), __byte_perm(w[k][3], w[k][2], 0x7610), __byte_perm(w[k][1], 0, 0x1032), __byte_perm(w[k][3], 0, 0x1032));
        }
        asm volatile("bar.sync 1, 256;" ::: "memory");
        const uint2* Tc = reinterpret_cast<const uint2*>(sm + CV_SM_T) + 16 + 76 * (warp & 2) + 8 * (warp & 1) + g - 2 * ti;
        uint2 fa[8][2], fn[8][2];
        auto near_taps = [&](uint2 (&f)[8][2], int c) {
#pragma unroll
            for (int m = 0; m < 8; m++) { f[m][0] = Tc[c * (TAPB / 8) + 16 * m]; f[m][1] = Tc[c * (TAPB / 8) + 16 * m - 8]; }
        };
        near_taps(fa, 3 * wgu);
        near_taps(fn, 2 - wgu);
        TSTAMP1X(12, 256); CST(0);
        uint32_t ya = smem_u32(sm + CV_SM_Y) + wgu * 8192 + (warp & 2) * 2048 + usw(2 * lane + (warp & 1)) * 16;
        uint64_t db = make_desc(smem_u32(Us + wgu * ULEN + UPADF), 16, 256, 3);
        if (wgu) asm volatile("bar.sync 6, 384;" ::: "memory");
        int c = wgu;
        auto chain = [&](const uint2 (&f)[8][2], auto&& meanwhile) {
            float acc[64];
            asm volatile("bar.sync %0, %1;" ::"r"(c ? 4 + wgu : 2), "r"(c ? 256 : 384) : "memory");
            TSTAMPC(1 + 3 * c);
            wgmma_fence();
#pragma unroll
            for (int m = 0; m < 8; m++) {
                wgmma_rs128(acc, f[m][0], f[m][1], db - (uint64_t)(2 * m), m);
                if (m == CV_HAND && c < 4) asm volatile("bar.arrive %0, 256;" ::"r"(5 - wgu) : "memory");
            }
            wgmma_commit();
            asm volatile("griddepcontrol.launch_dependents;" ::: "memory");
            TSTAMPC(2 + 3 * c); CST(13 + (c >> 1));
            meanwhile();
            wgmma_wait<0>();
            TSTAMPC(3 + 3 * c); CST(10 + (c >> 1));
            uint32_t w[16];
#pragma unroll
            for (int j = 0; j < 16; j++) w[j] = j ? pack2(acc[4 * j] + acc[4 * j - 2], acc[4 * j + 1] + acc[4 * j - 1]) : pack2(acc[0], acc[1]);
#pragma unroll
            for (int j = 0; j < 16; j += 4) stsm_x4_t(ya + 256 * j, w[j], w[j + 1], w[j + 2], w[j + 3]);
            __syncwarp();
            if (lane == 0) mbar_arrive(cnt + 8 * c);
            c += 2; ya += 16384; db += ULEN / 4;
        };
        const uint32_t e4 = lc.e4, e8 = e4 + 428 - 4 * g;
        uint2 fl[4];
        uint32_t kk;
#pragma unroll 1
        for (;;) {
            if (c != 1) chain(fa, [&] {
                if (c == 3 || warp + c == 12) {
#pragma unroll
                    for (int k = 0; k < 19; k++) (k < 16 ? fn[(k >> 1) & 7][k & 1] : fl[k & 3]) = make_uint2(lds1(k < 10 ? e4 + 32 * k + 16 : e8 + 32 * k - 304), lds1(k < 10 ? e4 + 32 * k : e8 + 32 * k - 320));
                    fl[3] = make_uint2(lds1(lc.en), lds1(lc.en - 64));
                    kk = lds1(smem_u32(sm + CV_SM_O) + 2048 * hc + 1672);
                }
            });
            if (c > 4) break;
            if (c == 2) asm volatile("bar.sync 7, 384;" ::: "memory");
            chain(fn, [&] { if (c == 2) near_taps(fa, 4); });
        }
        TSTAMP1X(6, 256); CST(2);
        if (wgu || warp == 8) {
            constexpr int seq[29] = {5, 6, 32, 7, 33, 8, 34, 9, 35, 10, 36, 11, 12, 13, 14, 15, 16, 17, 37, 18, 38, 19, 20, 21, 39, 22, 40, 23, 24};
            uint2 f[20];
#pragma unroll
            for (int k = 0; k < 20; k++) f[k] = k < 16 ? fn[(k >> 1) & 7][k & 1] : fl[k & 3];
            far(Int<10>(), seq, lc, hc, lane, f, kk);
        }
    } else {
        asm volatile("setmaxnreg.dec.sync.aligned.u32 88;");
        CV_IDX
        const uint4* ppv = piv + tid;
        const float4* psv = sum + tid;
        const uint2* pxv = reinterpret_cast<const uint2*>(x1T + (size_t)d0 * XCP) + (tid >> 4) * 32 + (tid & 15);
        asm volatile("st.shared.u64 [%0], %1;" ::"r"(smem_u32(Xs) + tid * 16), "l"((uint64_t)ppv ^ (uint64_t)psv ^ (uint64_t)pxv) : "memory");
        const int tc = (0x04302100 >> (4 * warp)) & 7;
        const Lc lc = lane_consts(lane, tc);
        pdl_sync();
        SPAN(3 + 4 * layer, 1);
        TSTAMP(0); CST(0);
        if (tid == 0) TSTAMPC(0);
        if (threadIdx.x == 0) { GSTAMP(g_tim, 15); }
        float4 sv[4];
#pragma unroll
        for (int k = 0; k < 4; k++)
            asm volatile("ld.relaxed.gpu.global.v4.f32 {%0,%1,%2,%3}, [%4];" : "=f"(sv[k].x), "=f"(sv[k].y), "=f"(sv[k].z), "=f"(sv[k].w) : "l"(psv + 256 * k) : "memory");
        uint4 pv;
        asm volatile("ld.relaxed.gpu.global.v4.u32 {%0,%1,%2,%3}, [%4];" : "=r"(pv.x), "=r"(pv.y), "=r"(pv.z), "=r"(pv.w) : "l"(ppv) : "memory");
        uint2 xe[CV_CPB], xo[CV_CPB];
#pragma unroll
        for (int c = 0; c < CV_CPB; c++) {
            asm volatile("ld.relaxed.gpu.global.v2.u32 {%0,%1}, [%2];" : "=r"(xe[c].x), "=r"(xe[c].y) : "l"(pxv + c * (XCP / 4)) : "memory");
            asm volatile("ld.relaxed.gpu.global.v2.u32 {%0,%1}, [%2];" : "=r"(xo[c].x), "=r"(xo[c].y) : "l"(pxv + c * (XCP / 4) + 16) : "memory");
        }
        constexpr float idm = 1.0f / DM;
        uint32_t mw[4];
        float rs[8];
#pragma unroll
        for (int k = 0; k < 4; k++) {
            const uint32_t pw = k == 0 ? pv.x : k == 1 ? pv.y : k == 2 ? pv.z : pv.w;
            const float d0_ = sv[k].x * idm, d1_ = sv[k].z * idm;
            mw[k] = pack2(__uint_as_float(pw << 16) + d0_, __uint_as_float(pw & 0xffff0000u) + d1_);
            const uint32_t vr = pack2(fmaxf(fmaf(-d0_, d0_, sv[k].y * idm), 0.f), fmaxf(fmaf(-d1_, d1_, sv[k].w * idm), 0.f));
            const uint32_t ve = pack2(__uint_as_float(vr << 16) + 1e-5f, __uint_as_float(vr & 0xffff0000u) + 1e-5f);
            const uint32_t sd = pack2(sqrt_apx(__uint_as_float(ve << 16)), sqrt_apx(__uint_as_float(ve & 0xffff0000u)));
            rs[2 * k] = rcp_apx(__uint_as_float(sd << 16)); rs[2 * k + 1] = rcp_apx(__uint_as_float(sd & 0xffff0000u));
        }
        if (rs[0] != 123.f) TSTAMP(13);
        const uint32_t ua = smem_u32(Us) + usw(tid + UPADF / 8) * 16;
        uint32_t uw[CV_CPB][4];
#pragma unroll
        for (int c = 0; c < CV_CPB; c++) {
            const uint32_t e0 = sub2(xe[c].x, mw[0]), e1 = sub2(xe[c].y, mw[1]), o0 = sub2(xo[c].x, mw[2]), o1 = sub2(xo[c].y, mw[3]);
            uw[c][0] = pack2(__uint_as_float(e0 << 16) * rs[0], __uint_as_float(o0 << 16) * rs[4]); uw[c][1] = pack2(__uint_as_float(e0 & 0xffff0000u) * rs[1], __uint_as_float(o0 & 0xffff0000u) * rs[5]);
            uw[c][2] = pack2(__uint_as_float(e1 << 16) * rs[2], __uint_as_float(o1 << 16) * rs[6]); uw[c][3] = pack2(__uint_as_float(e1 & 0xffff0000u) * rs[3], __uint_as_float(o1 & 0xffff0000u) * rs[7]);
            asm volatile("st.shared.v4.u32 [%0], {%1,%2,%3,%4};" ::"r"(ua + c * ULEN * 2), "r"(uw[c][0]), "r"(uw[c][1]), "r"(uw[c][2]), "r"(uw[c][3]) : "memory");
            if (c < 2) {
                fence_async_smem();
                asm volatile("bar.arrive %0, 384;" ::"r"(2 + 4 * c) : "memory");
                if (layer > 29 - c) __trap();
            }
        }
        fence_async_smem();
#pragma unroll
        for (int c = 0; c < CV_CPB; c++) *reinterpret_cast<uint4*>(Xs + c * XLEN + tid * 8) = make_uint4(xe[c].x, xe[c].y, xo[c].x, xo[c].y);
        asm volatile("bar.arrive 7, 384;" ::: "memory");
        asm volatile("bar.sync 3, 512;" ::: "memory");
        TSTAMP(1); CST(1);
        {
            auto box = [&](auto c0, auto c1, int chunk, int cb, bool full) {
                const uint32_t ea = smem_u32(Us + cb * ULEN) + usw(chunk + UPADF / 8 + (lane ? 1 : -1)) * 16, bx = smem_u32(sm + CV_SM_B + cb * BX_LEN) + chunk * 16;
                uint32_t lo[CV_CPB][4], hi[CV_CPB][2];
#pragma unroll
                for (int c = c0; c < c1; c++) {
                    lo[c][0] = 0;
#pragma unroll
                    for (int k = 1; k < 4; k++) lo[c][k] = __shfl_up_sync(~0u, uw[c][k], 1);
#pragma unroll
                    for (int k = 0; k < 2; k++) hi[c][k] = __shfl_down_sync(~0u, uw[c][k], 1);
                }
#pragma unroll
                for (int c = c0; c < c1; c++)
                    asm volatile("{\n.reg .pred p, q;\nsetp.eq.s32 p, %7, 0;\nsetp.eq.s32 q, %7, 31;\n@p ld.shared.v4.u32 {%0,%1,%2,%3}, [%6];\n@q ld.shared.v2.u32 {%4,%5}, [%6];\n}"
                                 : "+r"(lo[c][0]), "+r"(lo[c][1]), "+r"(lo[c][2]), "+r"(lo[c][3]), "+r"(hi[c][0]), "+r"(hi[c][1]) : "r"(ea + c * ULEN * 2), "r"(lane) : "memory");
#pragma unroll
                for (int c = c0; c < c1; c++) {
                    const uint32_t e[9] = {lo[c][1], lo[c][2], lo[c][3], uw[c][0], uw[c][1], uw[c][2], uw[c][3], hi[c][0], hi[c][1]};
                    uint32_t o[8], p[8], t[7], b3[5], b5[7];
#pragma unroll
                    for (int i = 0; i < 8; i++) { o[i] = __byte_perm(e[i], e[i + 1], 0x5432); p[i] = add2(e[i], o[i]); }
#pragma unroll
                    for (int i = 0; i < 5; i++) b3[i] = add2(o[i], p[i + 1]);
                    sts4(bx + c * BX_LEN + BX_3 + 160, b3);
#pragma unroll
                    for (int i = 1; i < 7; i++) { t[i] = add2(p[i], p[i + 1]); b5[i] = add2(t[i], e[i + 2]); }
                    sts4(bx + c * BX_LEN + BX_5 + 160, b5 + 2);
                    if (full) {
#pragma unroll
                        for (int i = 1; i < 5; i++) { b3[i] = add2(b3[i], t[i + 2]); t[i] = add2(t[i], b5[i + 2]); }
                        sts4(bx + c * BX_LEN + BX_7 + 272, b3 + 1);
                        sts4(bx + c * BX_LEN + BX_9 + 272, t + 1);
                    }
                }
            };
            auto reload = [&](int c, uint32_t a) { const uint4 v = lds4(a); uw[c][0] = v.x; uw[c][1] = v.y; uw[c][2] = v.z; uw[c][3] = v.w; };
            if (warp >= 6) {
#pragma unroll
                for (int c = 0; c < 3; c++) reload(c, ua - 1024 + (c + 2) * ULEN * 2);
            }
            if (warp >= 4) {
#pragma unroll
                for (int c = 3; c < 5; c++) reload(c, ua - 2048 + c * ULEN * 2);
            }
            box(Int<0>(), Int<3>(), warp < 6 ? tid : tid - 64, warp < 6 ? 0 : 2, warp < 4);
            if (warp >= 4) box(Int<3>(), Int<5>(), tid - 128, 0, true);
            else if (tid >= 128 - CV_CPB) {
                const int c = 127 - tid;
                const uint2 v = *reinterpret_cast<const uint2*>(Us + c * ULEN + UPADF);
                const float s1 = __uint_as_float(v.x << 16), s2 = s1 + __uint_as_float(v.x & 0xffff0000u), s3 = s2 + __uint_as_float(v.y << 16), s4 = s3 + __uint_as_float(v.y & 0xffff0000u);
                unsigned char* bc = sm + CV_SM_B + c * BX_LEN;
                *reinterpret_cast<uint32_t*>(bc + BX_5 + 156) = pack2(s1, s2);
                *reinterpret_cast<uint2*>(bc + BX_7 + 264) = make_uint2(v.x << 16, pack2(s2, s3));
                *reinterpret_cast<uint2*>(bc + BX_9 + 264) = make_uint2(pack2(s1, s2), pack2(s3, s4));
            }
        }
        __syncwarp();
        if (lane == 0) mbar_arrive(cnt + 40);
        TSTAMP(2); CST(2);
        if (layer && blockIdx.x == 0 && tid == 224) g_epoch = ld_epoch();
        __syncwarp();
        if ((0x6e >> warp) & 1) {
            constexpr int seq[16] = {0, 1, 2, 3, 4, 5, 6, 32, 7, 8, 9, 33, 10, 34, 11, 12};
            uint2 f[20];
            mbar_wait(cnt, 0);
            const uint32_t e8 = lc.e4 + 428 - (lane & 28);
#pragma unroll
            for (int k = 0; k < 13; k++) f[k] = make_uint2(lds1(k < 10 ? lc.e4 + 32 * k + 16 : e8 + 32 * k - 304), lds1(k < 10 ? lc.e4 + 32 * k : e8 + 32 * k - 320));
            f[19] = make_uint2(lds1(lc.en), lds1(lc.en - 64));
            far(Int<4>(), seq, lc, tc, lane, f, lds1(smem_u32(sm + CV_SM_O) + 2048 * tc + 1672));
        }
    }
    {
        CV_IDX
        if ((0xc91 >> warp) & 1) {
            const int c = __popc(0xc91 & ((1 << warp) - 1));
            uint4 xv[2], yv[2];
#pragma unroll
            for (int k = 0; k < 2; k++) xv[k] = lds4(smem_u32(Xs + c * XLEN) + 512 * k + lane * 16);
            const uint32_t u0 = lds1(smem_u32(Us + c * ULEN) + (lane == 31 ? UPADF * 2 : 0));
            mbar_wait(cnt + 8 * c, 0);
#pragma unroll
            for (int k = 0; k < 2; k++) yv[k] = lds4(smem_u32(sm + CV_SM_Y) + c * 8192 + 512 * k + usw(lane) * 16);
            const uint4 yz = lds4(smem_u32(sm + CV_SM_Y) + c * 8192 + 4096 + usw(lane) * 16);
            const float kk = __uint_as_float(lds1(smem_u32(sm + CV_SM_O) + 2048 * c + 1272) << 16);
            yv[1].x = add2(yv[1].x, yz.x); yv[1].y = add2(yv[1].y, yz.y); yv[1].z = add2(yv[1].z, yz.z);
            yv[1].w = pack2(fmaf(kk, __uint_as_float(u0 << 16), __uint_as_float(yv[1].w << 16) + __uint_as_float(yz.w << 16)),
                            fmaf(kk, __uint_as_float(u0 << 16) + __uint_as_float(u0 & 0xffff0000u), __uint_as_float(yv[1].w & 0xffff0000u) + __uint_as_float(yz.w & 0xffff0000u)));
#pragma unroll
            for (int k = 0; k < 2; k++) cv_store(dq + c * XCP * 2 + (lane >> 4) * 256 + (lane & 15) * 8 + 512 * k, xv[k], yv[k]);
        }
        TSTAMP(4); CST(8);
        if (layer == 1) {
            const int rb = (blockIdx.x >> 3) + (warp & 8) * 2, cg = blockIdx.x & 7, ch = (tid >> 3) & 31;
            const bf16* src = dst + (size_t)(cg * 80 + ch) * XCP + rb * 64 + (tid & 7) * 8;
            uint32_t v[3][4];
            __syncthreads();
            if (warp & 8) { const uint32_t c0 = clock(); while (clock() - c0 < 300) ; }
            uint32_t todo = (warp & 4) ? 3 : 7;
#pragma unroll 1
            for (int it = 0; it < SPIN_MAX; it++) {
#pragma unroll
                for (int k = 0; k < 3; k++)
                    if (todo >> k & 1)
                        asm volatile("ld.relaxed.gpu.global.v4.u32 {%0,%1,%2,%3}, [%4];" : "=r"(v[k][0]), "=r"(v[k][1]), "=r"(v[k][2]), "=r"(v[k][3]) : "l"(src + k * (32 * XCP)) : "memory");
#pragma unroll
                for (int k = 0; k < 3; k++)
                    if ((todo >> k & 1) && v[k][0] != ~0u && v[k][1] != ~0u && v[k][2] != ~0u && v[k][3] != ~0u) {
                        *reinterpret_cast<uint4*>(sm + (32 * k + ch) * 272 + ((tid & 7) + (warp & 8)) * 16) = make_uint4(v[k][0], v[k][1], v[k][2], v[k][3]);
                        todo ^= 1u << k;
                    }
                if (!todo) break;
                __nanosleep(CV_SLEEP);
            }
            __syncwarp();
            asm volatile("bar.sync %0, 256;" ::"r"(8 + (warp >> 3)) : "memory");
            uint32_t w[12];
#pragma unroll
            for (int k = 0; k < 3; k++) ldsm_x4(&w[4 * k], smem_u32(sm) + min(32 * k + lane, 79) * 272 + warp * 16);
            const uint32_t ot = smem_u32(sm + CV_SM_O) + warp * 1280, oa = ot + (lane & 7) * 160 + (lane >> 3) * 16;
            stsm_x4_t(oa, w[0], w[1], w[2], w[3]);
            stsm_x4_t(oa + 64, w[4], w[5], w[6], w[7]);
            asm volatile("stmatrix.sync.aligned.m8n8.x2.trans.shared.b16 [%0], {%1,%2};" ::"r"(oa + 128), "r"(w[8]), "r"(w[9]) : "memory");
            fence_async_smem();
            __syncwarp();
            if (lane == 0) {
                asm volatile("cp.async.bulk.tensor.3d.global.shared::cta.bulk_group [%0, {%1, %2, %3}], [%4];" ::"l"(&tmOut), "r"(cg * 80), "r"((rb >> 1) * 64 + 8 * (warp & 7)), "r"(rb & 1), "r"(ot) : "memory");
                asm volatile("cp.async.bulk.commit_group;" ::: "memory");
                asm volatile("cp.async.bulk.wait_group.read 0;" ::: "memory");
            }
        }
    }
    TSTAMP(3); CST(9); CST_END;
    GSTAMP(g_tim, 14);
    SPAN(3 + 4 * layer, 3);
}

template <int TA, int TB>
__device__ __forceinline__ void wgmma_n240(float (&d)[120], uint64_t da, uint64_t db, int acc) {
    asm volatile("{\n.reg .pred p;\nsetp.ne.b32 p, %124, 0;\nwgmma.mma_async.sync.aligned.m64n240k16.f32.bf16.bf16 {%0,%1,%2,%3,%4,%5,%6,%7,%8,%9,%10,%11,%12,%13,%14,%15,%16,%17,%18,%19,%20,%21,%22,%23,%24,%25,%26,%27,%28,%29,%30,%31,%32,%33,%34,%35,%36,%37,%38,%39,%40,%41,%42,%43,%44,%45,%46,%47,%48,%49,%50,%51,%52,%53,%54,%55,%56,%57,%58,%59,%60,%61,%62,%63,%64,%65,%66,%67,%68,%69,%70,%71,%72,%73,%74,%75,%76,%77,%78,%79,%80,%81,%82,%83,%84,%85,%86,%87,%88,%89,%90,%91,%92,%93,%94,%95,%96,%97,%98,%99,%100,%101,%102,%103,%104,%105,%106,%107,%108,%109,%110,%111,%112,%113,%114,%115,%116,%117,%118,%119}, %120, %121, p, 1, 1, %122, %123;\n}"
                 : "+f"(d[0]), "+f"(d[1]), "+f"(d[2]), "+f"(d[3]), "+f"(d[4]), "+f"(d[5]), "+f"(d[6]), "+f"(d[7]), "+f"(d[8]), "+f"(d[9]), "+f"(d[10]), "+f"(d[11]), "+f"(d[12]), "+f"(d[13]), "+f"(d[14]), "+f"(d[15]), "+f"(d[16]), "+f"(d[17]), "+f"(d[18]), "+f"(d[19]), "+f"(d[20]), "+f"(d[21]), "+f"(d[22]), "+f"(d[23]), "+f"(d[24]), "+f"(d[25]), "+f"(d[26]), "+f"(d[27]), "+f"(d[28]), "+f"(d[29]), "+f"(d[30]), "+f"(d[31]), "+f"(d[32]), "+f"(d[33]), "+f"(d[34]), "+f"(d[35]), "+f"(d[36]), "+f"(d[37]), "+f"(d[38]), "+f"(d[39]), "+f"(d[40]), "+f"(d[41]), "+f"(d[42]), "+f"(d[43]), "+f"(d[44]), "+f"(d[45]), "+f"(d[46]), "+f"(d[47]), "+f"(d[48]), "+f"(d[49]), "+f"(d[50]), "+f"(d[51]), "+f"(d[52]), "+f"(d[53]), "+f"(d[54]), "+f"(d[55]), "+f"(d[56]), "+f"(d[57]), "+f"(d[58]), "+f"(d[59]), "+f"(d[60]), "+f"(d[61]), "+f"(d[62]), "+f"(d[63]), "+f"(d[64]), "+f"(d[65]), "+f"(d[66]), "+f"(d[67]), "+f"(d[68]), "+f"(d[69]), "+f"(d[70]), "+f"(d[71]), "+f"(d[72]), "+f"(d[73]), "+f"(d[74]), "+f"(d[75]), "+f"(d[76]), "+f"(d[77]), "+f"(d[78]), "+f"(d[79]), "+f"(d[80]), "+f"(d[81]), "+f"(d[82]), "+f"(d[83]), "+f"(d[84]), "+f"(d[85]), "+f"(d[86]), "+f"(d[87]), "+f"(d[88]), "+f"(d[89]), "+f"(d[90]), "+f"(d[91]), "+f"(d[92]), "+f"(d[93]), "+f"(d[94]), "+f"(d[95]), "+f"(d[96]), "+f"(d[97]), "+f"(d[98]), "+f"(d[99]), "+f"(d[100]), "+f"(d[101]), "+f"(d[102]), "+f"(d[103]), "+f"(d[104]), "+f"(d[105]), "+f"(d[106]), "+f"(d[107]), "+f"(d[108]), "+f"(d[109]), "+f"(d[110]), "+f"(d[111]), "+f"(d[112]), "+f"(d[113]), "+f"(d[114]), "+f"(d[115]), "+f"(d[116]), "+f"(d[117]), "+f"(d[118]), "+f"(d[119])
                 : "l"(da), "l"(db), "n"(TA), "n"(TB), "r"(acc));
}

__device__ __forceinline__ void wgmma_n80(float (&d)[40], uint64_t da, uint64_t db, int acc) {
    asm volatile("{\n.reg .pred p;\nsetp.ne.b32 p, %42, 0;\nwgmma.mma_async.sync.aligned.m64n80k16.f32.bf16.bf16 {%0,%1,%2,%3,%4,%5,%6,%7,%8,%9,%10,%11,%12,%13,%14,%15,%16,%17,%18,%19,%20,%21,%22,%23,%24,%25,%26,%27,%28,%29,%30,%31,%32,%33,%34,%35,%36,%37,%38,%39}, %40, %41, p, 1, 1, 0, 1;\n}"
                 : "+f"(d[0]), "+f"(d[1]), "+f"(d[2]), "+f"(d[3]), "+f"(d[4]), "+f"(d[5]), "+f"(d[6]), "+f"(d[7]), "+f"(d[8]), "+f"(d[9]), "+f"(d[10]), "+f"(d[11]), "+f"(d[12]), "+f"(d[13]), "+f"(d[14]), "+f"(d[15]), "+f"(d[16]), "+f"(d[17]), "+f"(d[18]), "+f"(d[19]), "+f"(d[20]), "+f"(d[21]), "+f"(d[22]), "+f"(d[23]), "+f"(d[24]), "+f"(d[25]), "+f"(d[26]), "+f"(d[27]), "+f"(d[28]), "+f"(d[29]), "+f"(d[30]), "+f"(d[31]), "+f"(d[32]), "+f"(d[33]), "+f"(d[34]), "+f"(d[35]), "+f"(d[36]), "+f"(d[37]), "+f"(d[38]), "+f"(d[39])
                 : "l"(da), "l"(db), "r"(acc));
}

constexpr int A1_THREADS = 384;
constexpr int A1_NST = 4;
#define A1_SKEW 8
constexpr int A1_STAGE = 16384 + WQ_STAGE;
constexpr int A1_KVP = 336;
constexpr int A1_SM_KV = 2 * A1_STAGE;
constexpr int A1_SM_BAR = A1_NST * A1_STAGE;
constexpr int A1_SM_RS = A1_SM_BAR + 512;
constexpr int A1_SM_W0 = A1_SM_BAR + 3072, A1_SM_W3 = A1_SM_BAR - 3 * WOB, A1_SM_A1 = 2 * WOB, A1_SM_A0 = A1_SM_A1 + 61440;
constexpr int A1_SM_XA = A1_SM_W0 + 2 * WOB, A1_SM_XB = A1_SM_XA + 2048;
constexpr int A1_SMEM = A1_SM_W0 + 3 * WOB + CST_EXTRA;
static_assert(A1_SM_W3 >= A1_SM_KV + 144 * A1_KVP && A1_SM_W3 % 512 == 0 && A1_SM_A1 % 1024 == 0 && A1_SM_A0 <= A1_SM_KV && A1_SM_A0 + 61440 <= A1_SM_W3 && A1_SMEM <= 232448, "layout");
__device__ __forceinline__ constexpr uint32_t wo_off(int h) { return h * WOB + (h < 3 ? A1_SM_W0 : h < 6 ? A1_SM_W3 - 3 * WOB : -6 * WOB); }
#define A1_FRED "red.relaxed.gpu.global.add.u32"
#define A1_FLD "ld.acquire.gpu.global.u32"
#define ST_SLEEP 20
#define ST_SLEEP0 300
#define WO_LATE bar_done
#define A1_P0 2
#define A1_PW (kb - 2)
#define A1_FSPIN SPIN_MAX
#define A1_FSLEEP 40
#define YT_LAYER 1
#define WOT 352
#define A1_WOAT 6

template <int L>
__device__ __forceinline__ void a1_mainloop(float (&acc)[120], uint32_t sbase, uint32_t bars, int wg, int tile) {
    constexpr int layer = L; (void)layer;
    const uint64_t da0 = L ? make_desc(sbase + wg * 8192, 8192, 1024, 1) : make_desc(sbase + wg * 8192, 16, 1024, 1), db0 = make_desc(sbase + 16384, 1024, 256, 3);
#pragma unroll 1
    for (int t = 0;; t++) {
        const int st = t % A1_NST;
        mbar_wait(bars + 8 * st, (t / A1_NST) & 1);
        if (t == A1_SKEW && wg == 0) mbar_wait(bars + 160, 0);
        TSTAMP3(1 + t);
        if (t == 0) CSA(0);
        wgmma_fence();
#pragma unroll
        for (int kk = 0; kk < 4; kk++) wgmma_n240<L, 1>(acc, da0 + (uint32_t)(st * (A1_STAGE / 16) + kk * (L ? 128 : 2)), db0 + (uint32_t)(st * (A1_STAGE / 16) + (kk >> 1) * (WQ_STAGE / 32) + (kk & 1) * 32), kk ? 1 : t);
        wgmma_commit();
        if (t == 9) break;
        if (t == A1_SKEW - 1 && wg == 0) wgmma_wait<0>(); else wgmma_wait<1>();
        if (t > 0 && (threadIdx.x & 127) == 0) {
            if (t != A1_SKEW || wg) mbar_arrive(bars + 8 * (A1_NST + (t - 1) % A1_NST));
            if (t == A1_SKEW - 1 && wg == 0) mbar_arrive(bars + 8 * (A1_NST + t % A1_NST));
        }
    }
}

__global__ void __launch_bounds__(A1_THREADS, 1) a1_kernel(const int layer, const bf16* __restrict__ x0, const unsigned char* __restrict__ wq, const unsigned char* __restrict__ wo,
                                                           float2* __restrict__ rsum, uint4* __restrict__ of, const __grid_constant__ CUtensorMap tmX,
                                                           const __grid_constant__ CUtensorMap tmR, const __grid_constant__ CUtensorMap tmX1, const __grid_constant__ TileTab tab) {
    extern __shared__ __align__(1024) unsigned char stg[];
    const uint32_t sbase = smem_u32(stg);
    const uint32_t bars = sbase + A1_SM_BAR;
    const uint32_t bar_stat = bars + 64, bar_kv = bars + 72, bar_rd = bars + 168;
    const uint32_t bar_wo = bars + 208, bar_done = bars + 216, bar_pv = bars + 224, bar_kvf = bars + 232, bar_f2 = bars + 248, bar_e2 = bars + 384, que = bars + 448;
    const int tid = threadIdx.x;
    const int w = __shfl_sync(~0u, tid >> 5, 0), wg = w >> 2;
    uint32_t smid, ns;
    asm volatile("mov.u32 %0, %smid;" : "=r"(smid));
    asm volatile("mov.u32 %0, %nsmid;" : "=r"(ns));
    const auto te = tab.e[ns == tab.ns ? smid : 132 + blockIdx.x];
    const int tile = te.tile, mb = te.mb, hg = te.hg;
    float2* rst = reinterpret_cast<float2*>(stg + A1_SM_RS) + 8;
    auto issue_w = [&](int it) { bulk_load(sbase + (it % A1_NST) * A1_STAGE + 16384, wq + te.woff + it * WQ_STAGE, WQ_STAGE, bars + 8 * (it % A1_NST)); };
    auto issue_x = [&](int it, int kb) {
        asm volatile("cp.async.bulk.tensor.5d.shared::cluster.global.mbarrier::complete_tx::bytes [%0], [%1, {%3, %3, %3, %4, %5}], [%2];"
                     ::"r"(sbase + (it % A1_NST) * A1_STAGE), "l"(&tmX), "r"(bars + 8 * (it % A1_NST)), "r"(0), "r"(mb), "r"(kb) : "memory");
    };
    if (w == 8 && tile < 128) {
        const bool one = elect();
        if (one) {
#pragma unroll
            for (int i = 0; i < A1_NST; i++) mbar_init(bars + 8 * i, 1);
            asm volatile("fence.mbarrier_init.release.cluster;" ::: "memory");
        }
        __syncwarp();
        asm volatile("bar.arrive 0, 384;" ::: "memory");
        if (one) {
#define PW asm volatile("griddepcontrol.wait;" ::: "memory");
            if (layer) { issue_w(0); PW issue_x(0, te.kb0); issue_x(1, te.kb0 + 1); }
            else { issue_x(0, te.kb0); issue_x(1, te.kb0 + 1); PW issue_w(0); }
            issue_w(1);
#pragma unroll
            for (int i = 0; i < A1_NST; i++) mbar_expect_tx(bars + 8 * i, A1_STAGE);
            asm volatile("griddepcontrol.launch_dependents;" ::: "memory");
#pragma unroll
            for (int kb = 2; kb < A1_P0; kb++) { issue_x(kb, te.kb0 + kb); issue_w(kb); }
            DBGC(34); DBGV(33, smid); DBGV(40, t_entry); DBGV(30, t_a); DBGV(31, t_b); DBGV(32, t_c); DBGV(38, t_d); DBGV(39, t_e);
        }
    }
    if (tile >= 128) { sm_idle(layer); return; }
    if (wg == 2) {
        if (w != 8) {
            if (tid == 320) { prefetch_tmap(&tmX); prefetch_tmap(&tmR); prefetch_tmap(&tmX1); }
            asm volatile("bar.sync 0, 384;" ::: "memory");
        }
        if (w == 9) {
            asm volatile("bar.arrive 3, 64;" ::: "memory");
            if (layer == 0) pdl_sync();
            float4 a[2] = {};
#pragma unroll
            for (int k = 0; k < 10; k++)
#pragma unroll
                for (int h = 0; h < 2; h++) {
                    const int c4 = min(tid - 288 + 32 * h, 59);
                    const float4 v = __ldcg(reinterpret_cast<const float4*>(g_csp + k * 1920 + hg * 80) + c4 + (c4 / 20) * 140);
                    a[h].x += v.x; a[h].y += v.y; a[h].z += v.z; a[h].w += v.w;
                }
#pragma unroll
            for (int h = 0; h < 2; h++)
#pragma unroll
                for (int k = 0; k < 4; k++) {
                    const float c = 0.5f * (k == 0 ? a[h].x : k == 1 ? a[h].y : k == 2 ? a[h].z : a[h].w), c1 = c - rbf(c), c2 = c1 - rbf(c1);
                    *reinterpret_cast<uint4*>(stg + A1_SM_XB + (4 * min(tid - 288 + 32 * h, 59) + k) * 16) = make_uint4(pack2(c, c1), pack2(c2, 0.f), 0u, 0u);
                }
            fence_async_smem();
            __syncwarp();
            if (tid == 288) mbar_arrive(bar_stat);
            CSA(1);
#pragma unroll 4
            for (int k = 0; k < 40; k++) asm volatile("st.global.v4.u32 [%0], {%1,%1,%1,%1};" ::"l"(of + (mb * 8 + hg) * 1280 + 32 * k + (tid - 288)), "r"(~0u) : "memory");
            CSA(2);
            asm volatile("fence.acq_rel.gpu;" ::: "memory");
            asm volatile("fence.proxy.async.global;" ::: "memory");
            __syncwarp();
            if (tid == 288) mbar_arrive(bar_done);
            CSA(3);
            if (layer == YT_LAYER) {
#pragma unroll 4
                for (int k = tid - 288; k < 5 * XCP / 8; k += 32) asm volatile("st.global.v4.u32 [%0], {%1,%1,%1,%1};" ::"l"(reinterpret_cast<uint4*>(g_yT) + tile * (5 * XCP / 8) + k), "r"(~0u) : "memory");
            }
            TSTAMP1T(9, 288);
        } else if (w == 8) {
            asm volatile("bar.sync 3, 64;" ::: "memory");
            if (elect()) {
#pragma unroll 1
                for (int kb = A1_P0; kb < 10; kb++) {
                    if (kb < A1_NST) mbar_wait(bars + 8 * A1_PW, 0);
                    else {
                        mbar_wait(bars + 8 * (A1_NST + kb % A1_NST), ((kb / A1_NST) - 1) & 1);
                        if (layer && kb < 9) mbar_wait(bar_rd + 8 * (kb - A1_NST), 0);
                        mbar_expect_tx(bars + 8 * (kb % A1_NST), A1_STAGE);
                    }
                    issue_x(kb, kb < 5 ? kb + te.kb0 : kb - te.kb0); issue_w(kb);
                    if (kb == A1_WOAT) {
                        mbar_expect_tx(bar_wo, 8 * WOB);
                        bulk_load(sbase + A1_SM_W0, wo + hg * 8 * WOB, 2 * WOB, bar_wo);
                    }
                }
                TSTAMP1T(6, 256);
                mbar_wait(bars + 8 * (A1_NST + 3), 1);
                bulk_load(sbase + A1_SM_W3, wo + (hg * 8 + 3) * WOB, 3 * WOB, bar_wo);
            }
            __syncwarp();
        } else {
            const int j = tid - 320;
            const uint32_t tag = ld_epoch();
            if (tid == 352) sm_started(layer);
            if (layer == 0) {
                const uint4* src = reinterpret_cast<const uint4*>(x0 + (size_t)(mb * 128 + hg * 16 + (j >> 2)) * DM);
                uint4 v[20];
#pragma unroll
                for (int k = 0; k < 20; k++) v[k] = __ldg(src + (j & 3) + 4 * k);
                const float p0 = __uint_as_float(__shfl_sync(~0u, v[0].x, j & 28) << 16);
                float s[2] = {0.f, 0.f}, q[2] = {0.f, 0.f};
#pragma unroll
                for (int k = 0; k < 20; k++) {
                    const uint32_t w[4] = {v[k].x, v[k].y, v[k].z, v[k].w};
#pragma unroll
                    for (int i = 0; i < 4; i++) {
                        const float a = __uint_as_float(w[i] << 16) - p0, b = __uint_as_float(w[i] & 0xffff0000u) - p0;
                        s[0] += a; s[1] += b; q[0] = fmaf(a, a, q[0]); q[1] = fmaf(b, b, q[1]);
                    }
                }
                float s0 = s[0] + s[1], q0 = q[0] + q[1];
#pragma unroll
                for (int o = 1; o <= 2; o <<= 1) { s0 += __shfl_xor_sync(~0u, s0, o); q0 += __shfl_xor_sync(~0u, q0, o); }
                if ((j & 3) == 0) {
                    const float d = s0 * (1.0f / DM);
                    const uint32_t ms = pack2(p0 + d, sqrt_apx(rbf(rbf(fmaxf(fmaf(-d, d, q0 * (1.0f / DM)), 0.f)) + 1e-5f)));
                    asm volatile("st.global.cg.u64 [%0], %1;" ::"l"(g_rstat + mb * 128 + (j & 4) * 16 + hg * 8 + (j >> 3)), "l"(tagw(ms, tag)) : "memory");
                    g_piv[mb * 128 + hg * 16 + ((j >> 2) & 8) + (j & 4) + ((j >> 3) & 3)] = __ushort_as_bfloat16((unsigned short)ms);
                }
            }
            float o[4];
            int row;
            if (layer == 0) {
                ulonglong2 v;
#pragma unroll 1
                for (int it = 0; it < SPIN_MAX; it++) {
                    v = ld_tag2(reinterpret_cast<const ulonglong2*>(g_rstat + mb * 128) + j);
                    if (tag_ok(v, tag)) break;
                    __nanosleep(100);
                }
                o[0] = __uint_as_float((uint32_t)v.x << 16); o[1] = rcp_apx(__uint_as_float((uint32_t)v.x & 0xffff0000u));
                o[2] = __uint_as_float((uint32_t)v.y << 16); o[3] = rcp_apx(__uint_as_float((uint32_t)v.y & 0xffff0000u));
                row = 2 * j;
            } else {
                const int ch = j & 7, kg = (j >> 3) & 3;
                const unsigned char* src = stg + (j >> 5) * 8192 + (hg & 3) * 2048;
                float s[8], q[8], p0[8];
#pragma unroll
                for (int i = 0; i < 8; i++) { s[i] = 0.f; q[i] = 0.f; }
#pragma unroll 1
                for (int it = 0; it < 5; it++) {
                    uint4 v[4];
                    mbar_wait(bars + 8 * (it % A1_NST), it / A1_NST);
#pragma unroll
                    for (int k = 0; k < 4; k++) v[k] = *reinterpret_cast<const uint4*>(src + (it % A1_NST) * A1_STAGE + (4 * k + kg) * 128 + ((ch ^ ((4 * k + kg) & 7)) << 4));
                    if (it == 0) {
                        const uint4 pv = *reinterpret_cast<const uint4*>(src + (ch << 4));
                        const uint32_t w[4] = {pv.x, pv.y, pv.z, pv.w};
#pragma unroll
                        for (int i = 0; i < 4; i++) { p0[2 * i] = __uint_as_float(w[i] << 16); p0[2 * i + 1] = __uint_as_float(w[i] & 0xffff0000u); }
                    }
                    asm volatile("" :: "r"(v[0].x), "r"(v[1].x), "r"(v[2].x), "r"(v[3].x), "f"(p0[0]) : "memory");
                    __syncwarp();
                    if ((tid & 31) == 0) mbar_arrive(bar_rd + 8 * it);
#pragma unroll
                    for (int k = 0; k < 4; k++) {
                        const uint32_t w[4] = {v[k].x, v[k].y, v[k].z, v[k].w};
#pragma unroll
                        for (int i = 0; i < 4; i++) {
                            const float a = __uint_as_float(w[i] << 16) - p0[2 * i], b = __uint_as_float(w[i] & 0xffff0000u) - p0[2 * i + 1];
                            s[2 * i] += a; s[2 * i + 1] += b; q[2 * i] = fmaf(a, a, q[2 * i]); q[2 * i + 1] = fmaf(b, b, q[2 * i + 1]);
                        }
                    }
                }
#pragma unroll
                for (int i = 0; i < 4; i++) {
                    const bool up = kg & 2;
                    const float ss = __shfl_xor_sync(~0u, up ? s[i] : s[i + 4], 16), qq = __shfl_xor_sync(~0u, up ? q[i] : q[i + 4], 16);
                    s[i] = (up ? s[i + 4] : s[i]) + ss; q[i] = (up ? q[i + 4] : q[i]) + qq; p0[i] = up ? p0[i + 4] : p0[i];
                }
#pragma unroll
                for (int i = 0; i < 2; i++) {
                    const bool up = kg & 1;
                    const float ss = __shfl_xor_sync(~0u, up ? s[i] : s[i + 2], 8), qq = __shfl_xor_sync(~0u, up ? q[i] : q[i + 2], 8);
                    s[i] = (up ? s[i + 2] : s[i]) + ss; q[i] = (up ? q[i + 2] : q[i]) + qq; p0[i] = up ? p0[i + 2] : p0[i];
                }
                uint4* gp = g_halo + 86016 + mb * 512 + j;
                const float d0 = s[0] * (1.0f / 80.0f), d1 = s[1] * (1.0f / 80.0f);
                asm volatile("st.relaxed.gpu.global.v4.f32 [%0], {%1,%2,%3,%4};" ::"l"(gp + hg * 64), "f"(p0[0] + d0), "f"(fmaxf(fmaf(-d0, s[0], q[0]), 0.f)), "f"(p0[1] + d1), "f"(fmaxf(fmaf(-d1, s[1], q[1]), 0.f)) : "memory");
                __nanosleep(ST_SLEEP0);
                uint32_t pw[8][4], todo = 0xff;
#pragma unroll 1
                for (int it = 0; it < SPIN_MAX; it++) {
#pragma unroll
                    for (int k = 0; k < 8; k++)
                        if (todo >> k & 1) asm volatile("ld.relaxed.gpu.global.v4.u32 {%0,%1,%2,%3}, [%4];" : "=r"(pw[k][0]), "=r"(pw[k][1]), "=r"(pw[k][2]), "=r"(pw[k][3]) : "l"(gp + k * 64) : "memory");
#pragma unroll
                    for (int k = 0; k < 8; k++)
                        if (__all_sync(~0u, pw[k][0] != ~0u && pw[k][1] != ~0u && pw[k][2] != ~0u && pw[k][3] != ~0u)) todo &= ~(1u << k);
                    if (!todo) break;
                    __nanosleep(ST_SLEEP);
                }
#pragma unroll
                for (int r = 0; r < 2; r++) {
                    float mean = 0.f, m2 = 0.f;
#pragma unroll
                    for (int k = 0; k < 8; k++) mean += __uint_as_float(pw[k][2 * r]);
                    mean *= 0.125f;
#pragma unroll
                    for (int k = 0; k < 8; k++) {
                        const float dm = __uint_as_float(pw[k][2 * r]) - mean;
                        m2 += fmaf(80.0f * dm, dm, __uint_as_float(pw[k][2 * r + 1]));
                    }
                    o[2 * r] = rbf(mean);
                    o[2 * r + 1] = rcp_apx(rbf(sqrt_apx(rbf(rbf(m2 * (1.0f / DM)) + 1e-5f))));
                }
                row = (j >> 5) * 64 + (j & 7) * 8 + ((j >> 3) & 3) * 2;
                if (hg == 0) *reinterpret_cast<uint32_t*>(g_piv + SEQ + mb * 128 + 2 * (row & 60) + 4 * (row >> 6) + (row & 3)) = __byte_perm(__float_as_uint(o[0]), __float_as_uint(o[2]), 0x7632);
            }
#pragma unroll
            for (int r = 0; r < 2; r++)
                *reinterpret_cast<uint4*>(stg + A1_SM_XA + (row + r) * 16) = make_uint4(__byte_perm(__float_as_uint(-o[2 * r]), 0, 0x3232), __float_as_uint(-o[2 * r]) >> 16, 0u, 0u);
            *reinterpret_cast<float4*>(rst + row + (row >> 6) * 8) = make_float4(o[0], o[1], o[2], o[3]);
            fence_async_smem();
            TSTAMP1T(7, 320); CSA(1);
            if (tid == 320) DBGC(44);
            __syncwarp();
            if ((tid & 31) == 0) mbar_arrive(bar_stat);
        }
        CSA(4); CSA_END;
        if (tid == 320) DBGCAL(0);
        if (tid == WOT) {
            mbar_wait(WO_LATE, 0);
            mbar_wait(bar_done, 0);
            bulk_load(sbase, wo + (hg * 8 + 6) * WOB, 2 * WOB, bar_wo);
            bulk_load(sbase + A1_SM_W0 + 2 * WOB, wo + (hg * 8 + 2) * WOB, WOB, bar_wo);
        }
        __syncwarp();
#define FWA 11
#define FWB 10
        if (w == FWA || w == FWB) {
            const int cw = w == FWB;
            const uint32_t* fl = reinterpret_cast<const uint32_t*>(rsum + 2 * SEQ) + (((layer * 16 + mb) * 2 + cw) * 8 + (tid & 7)) * FSTR;
            const unsigned char* src = reinterpret_cast<const unsigned char*>(of) + mb * 163840 + cw * 10240 + (tid & 7) * 20480;
            const uint32_t sl = sbase + (cw ? A1_SM_A1 : A1_SM_A0);
            mbar_wait(cw ? bar_done : bar_kvf, 0);
            if ((tid & 31) == 0) {
                mbar_expect_tx(bar_f2 + 64 * cw + 64, 10240);
                tma_load_3d(sl + 51200, &tmR, layer ? 0 : hg * 80, layer ? hg * 80 : mb * 64, layer ? mb * 2 + cw : cw, bar_f2 + 64 * cw + 64);
            }
            __syncwarp();
            uint32_t pend = 0xffu & ~(1u << hg), v = 0;
            const uint32_t bo = wo_off((tid & 7) + ((tid & 7) < hg)) >> 4, lt = (1u << (tid & 31)) - 1;
#pragma unroll 1
            for (int it = 0; pend && it < 2 * SPIN_MAX; it++) {
                if (v != 4 && (pend >> (tid & 31) & 1)) asm volatile(A1_FLD " %0, [%1];" : "=r"(v) : "l"(fl) : "memory");
                uint32_t fr;
                asm volatile("{\n.reg .pred p;\nmbarrier.test_wait.parity.shared::cta.b64 p, [%1], 0;\nselp.b32 %0, 1, 0, p;\n}" : "=r"(fr) : "r"(bar_e2 + 16 * cw + (tid & 1) * 8) : "memory");
                fr = __ballot_sync(~0u, fr);
                uint32_t m = __ballot_sync(~0u, v == 4 || it >= A1_FSPIN) & pend;
                const int q = 8 - __popc(pend) + __popc(m & lt);
                m &= __ballot_sync(~0u, q < ((fr & 2) ? 8 : (fr & 1) ? 7 : 5));
                pend ^= m;
                if (m >> (tid & 31) & 1) DBGC(12 + cw * 8 + (tid & 7));
                if (!m) __nanosleep(A1_FSLEEP);
                else asm volatile("fence.proxy.async.global;" ::: "memory");
                if (m >> (tid & 31) & 1) {
                    bulk_load(q == 7 && !cw ? sbase + A1_SM_W0 : sl + (q < 6 ? q : q - 6) * 10240, src, 10240, bar_f2 + 64 * cw + 8 * q);
                    asm volatile("st.shared.u32 [%0], %1;" ::"r"(que + 32 * cw + 4 * q), "r"(bo) : "memory");
                    mbar_expect_tx(bar_f2 + 64 * cw + 8 * q, 10240);
                    DBGC(44 + cw * 8 + q);
                }
                __syncwarp();
            }
        }
    } else {
        if (tid == 0) {
            mbar_init(bar_stat, 3);
#pragma unroll
            for (int i = 0; i < 8; i++) mbar_init(bar_kv + 8 * i, 1);
            mbar_init(bars + 144, 1);
            mbar_init(bars + 160, 1);
#pragma unroll
            for (int i = 0; i < 5; i++) mbar_init(bar_rd + 8 * i, 2);
            asm volatile("fence.mbarrier_init.release.cluster;" ::: "memory");
        } else if (tid == 32) {
            mbar_init(bar_wo, 1); mbar_init(bar_done, 3); mbar_init(bar_pv, 4); mbar_init(bar_kvf, 8);
#pragma unroll
            for (int i = 0; i < 4; i++) { mbar_init(bar_e2 + 8 * i, i == 1 ? 2 : 1); mbar_init(bars + 8 * (A1_NST + i), 2); }
            asm volatile("fence.mbarrier_init.release.cluster;" ::: "memory");
        } else if (tid == 96) {
#pragma unroll
            for (int i = 0; i < 4; i++) mbar_init(bars + 416 + 8 * i, 1);
            asm volatile("fence.mbarrier_init.release.cluster;" ::: "memory");
        } else if (tid == 64) {
#pragma unroll
            for (int i = 1; i <= 16; i++) mbar_init(bar_f2 + 8 * i, 1);
            asm volatile("fence.mbarrier_init.release.cluster;" ::: "memory");
        }
        asm volatile("bar.sync 0, 384;" ::: "memory");
        SPAN(1 + 4 * layer, 0);
        constexpr int on = 1;
        float acc[120];
        const int lane = tid & 31, warp = w & 7, g = lane >> 2, t = lane & 3;
        if (on) {
            SPAN(1 + 4 * layer, 1);
            TSTAMP1(0);
            if (threadIdx.x == 0) { GSTAMP(g_tim1, 15); }
            TSTAMP3(0);
            if (tid == 0) TSTAMP2(0);
            TSTAMP4(0);
            if (tid == 0) DBGC(60);
            if (layer == 0) a1_mainloop<0>(acc, sbase, bars, wg, tile); else a1_mainloop<1>(acc, sbase, bars, wg, tile);
            uint32_t ok;
            asm volatile("{\n.reg .pred p;\nmbarrier.test_wait.parity.shared::cta.b64 p, [%1], 0;\nselp.b32 %0, 1, 0, p;\n}" : "=r"(ok) : "r"(bar_stat) : "memory");
            if (tid == 128 && !ok) mbar_arrive(bars + 160);
            __syncwarp();
            mbar_wait(bar_stat, 0);
            wgmma_fence();
            wgmma_n240<0, 0>(acc, make_desc(sbase + A1_SM_XA + wg * 1024, 0, 128, 0), make_desc(sbase + A1_SM_XB, 0, 128, 0), 1);
            wgmma_commit();
            if (tid == 128 && ok) mbar_arrive(bars + 160);
            mbar_wait(bars + 8 * (A1_NST + 3), 1);
        }
        const float2* rw = rst + 16 * warp + 8 * wg;
        const float rb0 = rw[g + 8].y, ra = rw[g].y * 0.22360679774997896f, rb = rb0 * 0.22360679774997896f;
        wgmma_wait<0>();
        if ((tid & 127) == 0) mbar_arrive(bar_done);
        TSTAMP1(2); CSA(1);
        TSTAMP1T(13, 224);
        if ((tid & 127) == 0) DBGC(62 - wg);
        uint32_t f[2][30];
#pragma unroll
        for (int j = 10; j < 30; j++) f[1][j] = pack2(acc[4 * j + 2], acc[4 * j + 3]);
        if ((warp & 3) == 3) {
            uint4* hout = g_halo + (((layer * 16 + mb) * 8 + hg) * 2 + wg) * 168;
#pragma unroll
            for (int j = 0; j < 20; j += 4)
                asm volatile("st.relaxed.gpu.global.v4.u32 [%0], {%1,%2,%3,%4};" ::"l"(hout + 8 * j + lane), "r"(f[1][10 + j]), "r"(f[1][11 + j]), "r"(f[1][12 + j]), "r"(f[1][13 + j]) : "memory");
            if (t == 0) asm volatile("st.relaxed.gpu.global.f32 [%0], %1;" ::"l"(reinterpret_cast<float*>(hout + 160) + g), "f"(rb0) : "memory");
        }
        TSTAMP1T(12, 224);
        const uint32_t kvw = sbase + A1_SM_KV + (16 * warp + 8 * wg) * A1_KVP;
        const uint32_t mrow = kvw + (lane & 7) * A1_KVP + (lane >> 3) * 16;
#pragma unroll
        for (int j = 0; j < 20; j += 4) stsm_x4(mrow + 16 * A1_KVP + 16 * j, f[1][10 + j], f[1][11 + j], f[1][12 + j], f[1][13 + j]);
        __syncwarp();
        if (lane == 0 && (warp & 3) != 3) mbar_arrive(bar_kv + 8 * (warp + 1));
#pragma unroll
        for (int j = 0; j < 30; j++) f[0][j] = pack2(acc[4 * j], acc[4 * j + 1]);
        stsm_x4(mrow + 8 * A1_KVP + 160, f[0][20], f[0][21], f[0][22], f[0][23]);
        stsm_x4(mrow + 8 * A1_KVP + 224, f[0][24], f[0][25], f[0][26], f[0][27]);
        asm volatile("stmatrix.sync.aligned.m8n8.x2.shared.b16 [%0], {%1,%2};" ::"r"(mrow + 8 * A1_KVP + 288), "r"(f[0][28]), "r"(f[0][29]) : "memory");
#pragma unroll
        for (int j = 0; j < 10; j++) f[1][j] = pack2(acc[4 * j + 2], acc[4 * j + 3]);
        __syncwarp();
        uint32_t vb[10][2], vp[12], kp[12];
#pragma unroll
        for (int j = 0; j < 10; j += 2) ldsm_x4_t(&vb[j][0], kvw + (8 + (lane & 15)) * A1_KVP + 160 + (lane >> 4) * 16 + 16 * j);
        const bool up0 = 2 * t > g, up1 = 2 * t + 1 > g, edge = (mb | (warp & 3)) == 0;
        float rk[4];
        auto above = [&]() {
            mbar_wait(bar_kv + 8 * warp, 0);
#pragma unroll
            for (int j = 0; j < 12; j += 4) ldsm_x4(&kp[j], mrow + 16 * j);
            rk[0] = rw[2 * t - (up0 ? 8 : 0)].y; rk[1] = rw[2 * t + 1 - (up1 ? 8 : 0)].y;
#pragma unroll
            for (int j = 0; j < 12; j += 4) ldsm_x4_t(&vp[j], mrow + 160 + 16 * j - (j == 8 ? (lane & 16) * 2 : 0));
            __syncwarp();
            if (lane == 0) mbar_arrive(bar_kvf);
        };
        auto halo = [&]() {
            if (lane == 0) mbar_arrive(bar_kvf);
            const uint4* hin = g_halo + (((layer * 16 + mb - 1) * 8 + hg) * 2 + wg) * 168;
            uint32_t hv[22] = {};
            rk[0] = rw[2 * t].y; rk[1] = rw[2 * t + 1].y;
            if (mb > 0) {
#pragma unroll 1
                for (int it = 0; it < SPIN_MAX; it++) {
#pragma unroll
                    for (int k = 0; k < 20; k += 4)
                        asm volatile("ld.relaxed.gpu.global.v4.u32 {%0,%1,%2,%3}, [%4];" : "=r"(hv[k]), "=r"(hv[k + 1]), "=r"(hv[k + 2]), "=r"(hv[k + 3]) : "l"(hin + 8 * k + lane) : "memory");
                    asm volatile("ld.relaxed.gpu.global.v2.u32 {%0,%1}, [%2];" : "=r"(hv[20]), "=r"(hv[21]) : "l"(reinterpret_cast<const uint2*>(hin + 160) + t) : "memory");
                    uint32_t m = max(hv[20], hv[21]);
#pragma unroll
                    for (int k = 0; k < 20; k += 2) m = __vimax3_u32(m, hv[k], hv[k + 1]);
                    if (!__any_sync(~0u, m == ~0u)) break;
                }
            }
            if (tid == 0) mbar_arrive(bars + 144);
            if (lane == 0) DBGC(52 - 16 * wg);
#pragma unroll
            for (int j = 0; j < 10; j++) {
                kp[j] = hv[j];
                asm volatile("movmatrix.sync.aligned.m8n8.trans.b16 %0, %1;" : "=r"(vp[j]) : "r"(hv[10 + j]));
            }
            if (up0) rk[0] = __uint_as_float(hv[20]);
            if (up1) rk[1] = __uint_as_float(hv[21]);
        };
        rk[2] = rw[2 * t + (up0 ? 0 : 8)].y; rk[3] = rw[2 * t + 1 + (up1 ? 0 : 8)].y;
        uint32_t qs[4][2];
#pragma unroll
        for (int h = 0; h < 4; h++) {
            qs[h][0] = (t >> 1) == (h & 1) ? f[0][5 * (h >> 1) + 2] : 0u; qs[h][1] = (t >> 1) == (h & 1) ? f[1][5 * (h >> 1) + 2] : 0u;
            asm volatile("" : "+r"(qs[h][0]), "+r"(qs[h][1]));
        }
#pragma unroll
        for (int j = 0; j < 10; j++) asm volatile("" : "+r"(f[0][j]), "+r"(f[1][j]), "+r"(f[0][10 + j]));
        if (warp & 3) above(); else if (wg) halo();
        TSTAMP1T(10, 64); CSA(2);
        if (warp && !wg) mbar_wait(bars + 416 + 8 * warp, 0);
        CSA(3);
        float sc[4][3][4];
#pragma unroll
        for (int h = 0; h < 4; h++) {
            const int jb = 5 * (h >> 1) + 3 * (h & 1), js = 5 * (h >> 1) + 2;
#pragma unroll
            for (int nt = 1; nt < 3; nt++) {
#pragma unroll
                for (int e = 0; e < 4; e++) sc[h][nt][e] = 0.f;
                mma_bf16(sc[h][nt], f[0][jb], f[1][jb], f[0][jb + 1], f[1][jb + 1], f[nt - 1][10 + jb], f[nt - 1][11 + jb]);
                mma_bf16_k8(sc[h][nt], qs[h][0], qs[h][1], f[nt - 1][10 + js]);
            }
        }
        if (warp == 0) halo();
        TSTAMP1(8); CSA(4);
#pragma unroll
        for (int h = 0; h < 4; h++) {
            const int jb = 5 * (h >> 1) + 3 * (h & 1), js = 5 * (h >> 1) + 2;
#pragma unroll
            for (int e = 0; e < 4; e++) sc[h][0][e] = 0.f;
            mma_bf16(sc[h][0], f[0][jb], f[1][jb], f[0][jb + 1], f[1][jb + 1], kp[jb], kp[jb + 1]);
            mma_bf16_k8(sc[h][0], qs[h][0], qs[h][1], kp[js]);
        }
        TSTAMP1T(3, 64);
        float p[4][4], sum[4][2];
        uint32_t lg[4][2], mx[4];
        const float rl[4] = {rk[0] * ra, rk[1] * ra, rk[2] * rb, rk[3] * rb};
        auto max2 = [](uint32_t a, uint32_t b) { uint32_t r; asm("max.bf16x2 %0, %1, %2;" : "=r"(r) : "r"(a), "r"(b)); return r; };
#pragma unroll
        for (int h = 0; h < 4; h++) {
            lg[h][0] = pack2((up0 ? sc[h][0][0] : sc[h][1][0]) * rl[0], (up0 ? sc[h][1][2] : sc[h][2][2]) * rl[2]);
            lg[h][1] = pack2((up1 ? sc[h][0][1] : sc[h][1][1]) * rl[1], (up1 ? sc[h][1][3] : sc[h][2][3]) * rl[3]);
            if (edge) {
                if (up0) lg[h][0] = __byte_perm(lg[h][0], 0xce6eu, 0x3254);
                if (up1) lg[h][1] = __byte_perm(lg[h][1], 0xce6eu, 0x3254);
            }
            mx[h] = max2(lg[h][0], lg[h][1]);
        }
#pragma unroll
        for (int o = 1; o <= 2; o <<= 1)
#pragma unroll
            for (int h = 0; h < 4; h++) mx[h] = max2(mx[h], __shfl_xor_sync(~0u, mx[h], o));
#pragma unroll
        for (int h = 0; h < 4; h++)
#pragma unroll
            for (int r = 0; r < 2; r++) {
                const float m = __uint_as_float(r ? mx[h] & 0xffff0000u : mx[h] << 16);
#pragma unroll
                for (int e = 0; e < 2; e++)
                    asm("ex2.approx.ftz.f32 %0, %1;" : "=f"(p[h][2 * r + e]) : "f"((__uint_as_float(r ? lg[h][e] & 0xffff0000u : lg[h][e] << 16) - m) * 1.4426950408889634f));
                sum[h][r] = p[h][2 * r] + p[h][2 * r + 1];
            }
#pragma unroll
        for (int o = 1; o <= 2; o <<= 1)
#pragma unroll
            for (int h = 0; h < 4; h++)
#pragma unroll
                for (int r = 0; r < 2; r++) sum[h][r] += __shfl_xor_sync(~0u, sum[h][r], o);
        TSTAMP1T(5, 64); CSA(5);
        const uint32_t mu = (up0 ? 0xffffu : 0u) | (up1 ? 0xffff0000u : 0u);
        uint32_t ob[10][2];
#pragma unroll
        for (int P = 0; P < 2; P++) {
            float os[2][4];
#pragma unroll
            for (int e = 0; e < 2; e++) {
                const int h = 2 * P + e;
                const float i0 = rcp_apx(sum[h][0]), i1 = rcp_apx(sum[h][1]);
                const uint32_t w0 = pack2(p[h][0] * rk[0] * i0, p[h][1] * rk[1] * i0), w1 = pack2(p[h][2] * rk[2] * i1, p[h][3] * rk[3] * i1);
#pragma unroll
                for (int dt = 0; dt < 3; dt++) {
                    const int j = 5 * P + (dt < 2 ? 3 * e + dt : 2);
                    float o[4] = {0.f, 0.f, 0.f, 0.f};
                    mma_bf16(o, w0 & ~mu, w1 & mu, 0u, w1 & ~mu, vb[j][0], vb[j][1]);
                    mma_bf16_k8(o, w0 & mu, 0u, vp[j]);
                    if (dt < 2) { ob[j][0] = pack2(o[0], o[1]); ob[j][1] = pack2(o[2], o[3]); }
                    else { os[e][0] = o[0]; os[e][1] = o[1]; os[e][2] = o[2]; os[e][3] = o[3]; }
                }
            }
#pragma unroll
            for (int k = 0; k < 4; k++) os[0][k] = t < 2 ? os[0][k] : os[1][k];
            ob[5 * P + 2][0] = pack2(os[0][0], os[0][1]); ob[5 * P + 2][1] = pack2(os[0][2], os[0][3]);
        }
        const uint32_t sl = sbase + (wg ? A1_SM_A1 : A1_SM_A0);
        const uint32_t o0 = (warp & 3) * 2048 + g * 64 + ((t ^ (g >> 1)) << 4), o1 = 8192 + (warp & 3) * 512 + g * 32 + ((t ^ ((g >> 2) << 1)) << 3);
        CSA(15);
        mbar_wait(bar_done, 0);
        if (wg == 0) mbar_wait(bar_kvf, 0);
#pragma unroll
        for (int h = 0; h < 2; h++) {
            asm volatile("st.shared.v4.u32 [%0], {%1,%2,%3,%4};" ::"r"(sl + o0 + h * 1024), "r"(ob[0][h]), "r"(ob[1][h]), "r"(ob[2][h]), "r"(ob[3][h]) : "memory");
            asm volatile("st.shared.v4.u32 [%0], {%1,%2,%3,%4};" ::"r"(sl + o0 + h * 1024 + 512), "r"(ob[4][h]), "r"(ob[5][h]), "r"(ob[6][h]), "r"(ob[7][h]) : "memory");
            asm volatile("st.shared.v2.u32 [%0], {%1,%2};" ::"r"(sl + o1 + h * 256), "r"(ob[8][h]), "r"(ob[9][h]) : "memory");
        }
        if (wg && lane == 0) mbar_arrive(bars + 384 + 8 * warp);
        fence_async_smem();
        __syncwarp();
        TSTAMP1T(4, 64); CSA(6);
        TSTAMP1(1);
        TSTAMP2(1);
        const unsigned char* ot = reinterpret_cast<const unsigned char*>(of) + mb * 163840 + wg * 10240;
        if (lane == 0) {
            asm volatile("cp.async.bulk.global.shared::cta.bulk_group [%0], [%1], 2048;" ::"l"(ot + hg * 20480 + (warp & 3) * 2048), "r"(sl + (warp & 3) * 2048) : "memory");
            asm volatile("cp.async.bulk.global.shared::cta.bulk_group [%0], [%1], 512;" ::"l"(ot + hg * 20480 + 8192 + (warp & 3) * 512), "r"(sl + 8192 + (warp & 3) * 512) : "memory");
            asm volatile("cp.async.bulk.commit_group;" ::: "memory");
            if (wg == 0) mbar_arrive(bar_pv);
            asm volatile("cp.async.bulk.wait_group 0;" ::: "memory");
            asm volatile(A1_FRED " [%0], 1;" ::"l"(reinterpret_cast<uint32_t*>(rsum + 2 * SEQ) + (((layer * 16 + mb) * 2 + wg) * 8 + hg) * FSTR) : "memory");
            DBGC(4 + warp);
        }
        TSTAMP4(11); CSA(7);
        float ac2[40];
        const uint64_t db0 = make_desc(sbase, 1024, 256, 3), db1 = make_desc(sbase + 10240, 512, 256, 3), da0 = make_desc(sl, 16, 1024, 2), da1 = make_desc(sl + 8192, 16, 256, 3);
        const uint32_t o7 = wg ? 640 : (A1_SM_W0 - A1_SM_A0) >> 4;
        const uint32_t trow = ((lane & 7) + 8 * (lane >> 4)) * 128 + (((2 * (warp & 3) + ((lane >> 3) & 1)) ^ (lane & 7)) << 4);
        uint32_t xr[10][2];
        mbar_wait(bar_f2 + 64 * wg + 64, 0);
        if (layer == 0) {
#pragma unroll
            for (int j = 0; j < 10; j += 2) ldsm_x4(&xr[j][0], sl + 51200 + (16 * (warp & 3) + (lane & 15)) * 160 + (lane >> 4) * 16 + 16 * j);
        } else {
#pragma unroll
            for (int j = 0; j < 10; j += 2) ldsm_x4_t(&xr[j][0], sl + 51200 + trow + 1024 * j);
        }
        const uint32_t ri = __shfl_sync(~0u, layer * SEQ + (wg * 2 + ((g >> 1) & 1)) * 512 + (mb * 16 + 4 * (warp & 3) + (g >> 2)) * 2 + (g & 1), lane);
        mbar_wait(bar_wo, 0);
        if (wg) mbar_wait(bar_pv, 0);
        if (wg) asm volatile("bar.sync 2, 128;" ::: "memory"); else asm volatile("bar.sync 1, 128;" ::: "memory");
        TSTAMP2(2); CSA(8);
#pragma unroll
        for (int q = 0; q < 8; q++) {
            uint32_t bo = wo_off(0) >> 4;
            if (q) {
                mbar_wait(bar_f2 + 64 * wg + 8 * q, 0);
                asm volatile("ld.shared.u32 %0, [%1];" : "=r"(bo) : "r"(que + 32 * wg + 4 * q) : "memory");
                bo = __shfl_sync(~0u, bo, 0);
                TSTAMP4(q);
                if (q % 3 == 1) CSA(9 + q / 3);
                if (q == 1 && (tid & 127) == 0) DBGC(29 + 8 * wg);
            }
            wgmma_fence();
#pragma unroll
            for (int j = 0; j < 5; j++) wgmma_n80(ac2, (j < 4 ? da0 : da1) + (q == 7 ? o7 : 0u) + (uint64_t)((q < 6 ? q * 640 : 0) + (j & 2) * 16 + (j & 1) * 2), (j < 4 ? db0 : db1) + bo + (uint64_t)((j & 2) * 160 + (j & 1) * 32), j || q);
            wgmma_commit();
            if (q == 0) {
                wgmma_wait<0>();
                if ((tid & 127) == 0) { mbar_arrive(bar_e2 + 16 * wg); mbar_arrive(bar_e2 + 8); }
            }
            if (q == 2 && wg) {
                wgmma_wait<1>();
                if (tid == 128) mbar_arrive(bar_e2 + 24);
            }
        }
        if ((tid & 127) == 0) DBGC(28 + wg * 8 + 7);
        TSTAMP2(3);
        wgmma_wait<0>();
        TSTAMP2(4); CSA(12);
        if (__any_sync(~0u, ac2[0] != ac2[0] || ac2[2] != ac2[2])) {
#pragma unroll
            for (int i = 0; i < 40; i++) ac2[i] = 0.f;
            uint32_t a[20], an[20];
            auto lda = [&](uint32_t (&r)[20], int h) {
#pragma unroll
                for (int u = 0; u < 4; u++)
                    asm volatile("ld.relaxed.gpu.global.v4.u32 {%0,%1,%2,%3}, [%4];" : "=r"(r[4 * u]), "=r"(r[4 * u + 1]), "=r"(r[4 * u + 2]), "=r"(r[4 * u + 3]) : "l"(ot + h * 20480 + o0 + u * 512) : "memory");
#pragma unroll
                for (int u = 0; u < 2; u++)
                    asm volatile("ld.relaxed.gpu.global.v2.u32 {%0,%1}, [%2];" : "=r"(r[16 + 2 * u]), "=r"(r[17 + 2 * u]) : "l"(ot + h * 20480 + o1 + u * 256) : "memory");
            };
            lda(an, 0);
#pragma unroll 5
            for (int k = lane; k < WOB / 16; k += 32)
                reinterpret_cast<uint4*>(stg + (sl - sbase))[k] = __ldcg(reinterpret_cast<const uint4*>(wo + hg * 8 * WOB) + k);
            __syncwarp();
#pragma unroll 1
            for (int h = 0; h < 8; h++) {
#pragma unroll 1
                for (int it = 0; it < SPIN_MAX; it++) {
                    uint32_t m = 0;
#pragma unroll
                    for (int k = 0; k < 20; k += 2) m = __vimax3_u32(m, an[k], an[k + 1]);
                    if (!__any_sync(~0u, m == ~0u)) break;
                    lda(an, h);
                }
#pragma unroll
                for (int k = 0; k < 20; k++) a[k] = an[k];
                lda(an, min(h + 1, 7));
                const uint32_t bp = h == hg ? sl : sbase + wo_off(h + (h < hg));
                const int r0 = 8 * ((lane & 7) >> 1) + 2 * (lane >> 3) + (lane & 1), r2 = 4 * ((lane & 7) >> 1) + 2 * ((lane >> 3) & 1) + (lane & 1);
#pragma unroll
                for (int n = 0; n < 10; n++) {
                    uint32_t b[12];
                    ldsm_x4_t(b, bp + (n >> 1) * 1024 + r0 * 32 + (((n ^ (r0 >> 2)) & 1) << 4));
                    ldsm_x4_t(b + 4, bp + 5120 + (n >> 1) * 1024 + r0 * 32 + (((n ^ (r0 >> 2)) & 1) << 4));
                    ldsm_x4_t(b + 8, bp + 10240 + (n >> 1) * 512 + r2 * 32 + (((n ^ (r2 >> 2)) & 1) << 4));
                    mma_bf16(ac2 + 4 * n, a[0], a[8], a[1], a[9], b[0], b[1]); mma_bf16(ac2 + 4 * n, a[2], a[10], a[3], a[11], b[2], b[3]);
                    mma_bf16(ac2 + 4 * n, a[4], a[12], a[5], a[13], b[4], b[5]); mma_bf16(ac2 + 4 * n, a[6], a[14], a[7], a[15], b[6], b[7]);
                    mma_bf16(ac2 + 4 * n, a[16], a[18], a[17], a[19], b[8], b[9]);
                }
            }
        }
#pragma unroll
        for (int j = 0; j < 10; j++)
#pragma unroll
            for (int hh = 0; hh < 2; hh++) {
                const uint32_t a = pack2(ac2[4 * j + 2 * hh], ac2[4 * j + 2 * hh + 1]);
                const __nv_bfloat162 r = __hadd2_rn(*reinterpret_cast<const __nv_bfloat162*>(&xr[j][hh]), *reinterpret_cast<const __nv_bfloat162*>(&a));
                xr[j][hh] = *reinterpret_cast<const uint32_t*>(&r);
            }
        const uint32_t so = sl + 30720;
#pragma unroll
        for (int j = 0; j < 10; j += 2) stsm_x4_t(so + trow + 1024 * j, xr[j][0], xr[j][1], xr[j + 1][0], xr[j + 1][1]);
        fence_async_smem();
        if (wg) asm volatile("bar.sync 2, 128;" ::: "memory"); else asm volatile("bar.sync 1, 128;" ::: "memory");
        TSTAMP2(5); CSA(13);
        if ((tid & 127) == 0) {
            asm volatile("cp.async.bulk.tensor.2d.global.shared::cta.bulk_group [%0, {%1, %2}], [%3];" ::"l"(&tmX1), "r"(mb * 128 + 64 * wg), "r"(hg * 80), "r"(so) : "memory");
            asm volatile("cp.async.bulk.commit_group;" ::: "memory");
        }
        __syncwarp();
        const float p0 = *(volatile const float*)&rw[g].x, p1 = *(volatile const float*)&rw[g + 8].x;
        float s[3][4] = {};
        const uint32_t pp[2] = {__byte_perm(__float_as_uint(p0), 0, 0x3232), __byte_perm(__float_as_uint(p1), 0, 0x3232)};
#pragma unroll
        for (int j = 0; j < 10; j += 2) {
            const uint32_t d0 = sub2(xr[j][0], pp[0]), d1 = sub2(xr[j][1], pp[1]), d2 = sub2(xr[j + 1][0], pp[0]), d3 = sub2(xr[j + 1][1], pp[1]);
            mma_bf16(s[0], xr[j][0], xr[j][1], xr[j + 1][0], xr[j + 1][1], 0x3f803f80u, 0x3f803f80u);
            mma_bf16(s[1], d0, d1, d2, d3, d0, d2);
            mma_bf16(s[2], d0, d1, d2, d3, d1, d3);
        }
        if (t == (g >> 1)) {
            float2* rp = rsum + ri;
            asm volatile("red.relaxed.gpu.global.add.v2.f32 [%0], {%1, %2};" ::"l"(rp), "f"(fmaf(-80.f, p0, s[0][0])), "f"((g & 1) ? s[1][1] : s[1][0]) : "memory");
            asm volatile("red.relaxed.gpu.global.add.v2.f32 [%0], {%1, %2};" ::"l"(rp + 4), "f"(fmaf(-80.f, p1, s[0][2])), "f"((g & 1) ? s[2][3] : s[2][2]) : "memory");
        }
        asm volatile("cp.async.bulk.wait_group.read 0;" ::: "memory");
        TSTAMP2(6); CSA(14); CSA_END;
        if (tid == 0) DBGC(63);
        if (tid == 128) DBGC(28);
        if (tid == 0) DBGCAL(2);
        GSTAMP(g_tim1, 14);
        SPAN(1 + 4 * layer, 3);
    }
}

static int h_nsm;
static void* h_sym[11];
static TileTab h_tab;
static CUtensorMap h_tmX0, h_tmX1, h_tmR0, h_tmR1, h_tmX1st, h_tmOut, h_tmWq, h_tmWo, h_tmWt;
typedef CUresult (*PFN_encodeTiled)(CUtensorMap*, CUtensorMapDataType, cuuint32_t, void*, const cuuint64_t*, const cuuint64_t*,
                                    const cuuint32_t*, const cuuint32_t*, CUtensorMapInterleave, CUtensorMapSwizzle,
                                    CUtensorMapL2promotion, CUtensorMapFloatOOBfill);
static void make_tmap(CUtensorMap* tm, const void* ptr, uint64_t cols, uint64_t rows, uint32_t bc, uint32_t br, CUtensorMapSwizzle sw, uint64_t pitch = 0, uint64_t hi = 0, uint32_t bh = 2) {
    static PFN_encodeTiled fn = nullptr;
    if (!fn) {
        void* p = nullptr; cudaDriverEntryPointQueryResult qr;
        cudaGetDriverEntryPoint("cuTensorMapEncodeTiled", &p, cudaEnableDefault, &qr);
        fn = (PFN_encodeTiled)p;
    }
    if (br == 0) {
        cuuint64_t dims[5] = {16, 2, rows / 8, 4, cols / 16}; cuuint64_t strides[4] = {cols * 2, cols * 16, cols * 4, 32};
        cuuint32_t box[5] = {16, 2, bc, 4, 5}; cuuint32_t es[5] = {1, 1, 1, 1, 1};
        fn(tm, CU_TENSOR_MAP_DATA_TYPE_BFLOAT16, 5, const_cast<void*>(ptr), dims, strides, box, es, CU_TENSOR_MAP_INTERLEAVE_NONE, sw,
           CU_TENSOR_MAP_L2_PROMOTION_L2_128B, CU_TENSOR_MAP_FLOAT_OOB_FILL_NONE);
        return;
    }
    if (bh == 0) {
        cuuint64_t dims[5] = {64, 64, 2, 16, 10}; cuuint64_t strides[4] = {pitch * 2, hi * 2, cols * 2, rows * 2};
        cuuint32_t box[5] = {64, 64, 2, 1, 1}; cuuint32_t es[5] = {1, 1, 1, 1, 1};
        fn(tm, CU_TENSOR_MAP_DATA_TYPE_BFLOAT16, 5, const_cast<void*>(ptr), dims, strides, box, es, CU_TENSOR_MAP_INTERLEAVE_NONE, sw,
           CU_TENSOR_MAP_L2_PROMOTION_L2_128B, CU_TENSOR_MAP_FLOAT_OOB_FILL_NONE);
        return;
    }
    if (hi) {
        cuuint64_t dims[3] = {cols, rows, hi == 64 ? 32u : hi == 16 ? 120u : 2u}; cuuint64_t strides[2] = {pitch * 2, hi * 2};
        cuuint32_t box[3] = {bc, br, bh}; cuuint32_t es[3] = {1, 1, 1};
        fn(tm, CU_TENSOR_MAP_DATA_TYPE_BFLOAT16, 3, const_cast<void*>(ptr), dims, strides, box, es, CU_TENSOR_MAP_INTERLEAVE_NONE, sw,
           CU_TENSOR_MAP_L2_PROMOTION_L2_128B, CU_TENSOR_MAP_FLOAT_OOB_FILL_NONE);
        return;
    }
    cuuint64_t dims[2] = {cols, rows}; cuuint64_t strides[1] = {(pitch ? pitch : cols) * 2};
    cuuint32_t box[2] = {bc, br}; cuuint32_t es[2] = {1, 1};
    fn(tm, CU_TENSOR_MAP_DATA_TYPE_BFLOAT16, 2, const_cast<void*>(ptr), dims, strides, box, es, CU_TENSOR_MAP_INTERLEAVE_NONE, sw,
       CU_TENSOR_MAP_L2_PROMOTION_L2_128B, CU_TENSOR_MAP_FLOAT_OOB_FILL_NONE);
}
template <typename... Args>
static void launch_pdl(void (*kern)(Args...), int grid, int block, int smem, Args... args) {
    cudaLaunchConfig_t cfg = {};
    cfg.gridDim = dim3(grid); cfg.blockDim = dim3(block); cfg.dynamicSmemBytes = smem; cfg.stream = cudaStreamPerThread;
    cudaLaunchAttribute at[1];
    at[0].id = cudaLaunchAttributeProgrammaticStreamSerialization; at[0].val.programmaticStreamSerializationAllowed = 1;
    cfg.attrs = at; cfg.numAttrs = 1;
    cudaLaunchKernelEx(&cfg, kern, args...);
}
static void launch_stage(int k, void* const* d_in, void* d_out) {
    const KgIn kg = {(const bf16*)d_in[4], (const bf16*)d_in[5], (const bf16*)d_in[6], (const bf16*)d_in[7], (const bf16*)d_in[8], (const bf16*)d_in[9], (const bf16*)d_in[0], (const bf16*)d_in[1], (const bf16*)d_in[2],
                      (uint4*)h_sym[0], (uint4*)h_sym[1], (uint4*)h_sym[2], (uint4*)h_sym[3], (uint4*)h_sym[4], (float*)h_sym[5]};
    switch (k) {
        case 0: kgen_kernel<<<128, 512, KG_SMEM, cudaStreamPerThread>>>(kg, h_tmWq, h_tmWo, h_tmWt); break;
        case 1: launch_pdl(a1_kernel, h_nsm, A1_THREADS, A1_SMEM, 0, (const bf16*)d_in[0], (const unsigned char*)h_sym[1], (const unsigned char*)h_sym[2], (float2*)h_sym[4], (uint4*)h_sym[6], h_tmX0, h_tmR0, h_tmX1st, h_tab); break;
        case 3: launch_pdl(conv_kernel, DM / CV_CPB, CV_THREADS, CV_SMEM, 0, (const uint4*)h_sym[7], (const float4*)h_sym[4], (const bf16*)h_sym[8], (bf16*)h_sym[9], (const uint4*)h_sym[0], h_tmOut); break;
        case 5: launch_pdl(a1_kernel, h_nsm, A1_THREADS, A1_SMEM, 1, (const bf16*)d_in[0], (const unsigned char*)h_sym[1], (const unsigned char*)h_sym[2], (float2*)h_sym[4], (uint4*)h_sym[6], h_tmX1, h_tmR1, h_tmX1st, h_tab); break;
        case 7: launch_pdl(conv_kernel, DM / CV_CPB, CV_THREADS, CV_SMEM, 1, (const uint4*)h_sym[7] + SEQ / 8, (const float4*)h_sym[4] + SEQ / 2, (const bf16*)h_sym[8], (bf16*)h_sym[10], (const uint4*)h_sym[0], h_tmOut); break;
        default: break;
    }
}
static int n_stage_kernels() { return 9; }
static const char* stage_name(int k) { const char* n[] = {"kgen", "a1", "a2", "conv", "tr", "a1", "a2", "conv", "tr"}; return n[k]; }

extern "C" void kernel_launch(void* const* d_in, const int* in_sizes, int n_in, void* d_out, int out_size) {
    (void)in_sizes; (void)n_in; (void)out_size;
    static const void *p_in = nullptr, *p_w1 = nullptr, *p_w2 = nullptr, *p_out = nullptr;
    if (p_in != d_in[0] || p_w1 != d_in[1] || p_w2 != d_in[2] || p_out != d_out) {
        cudaFuncSetAttribute(conv_kernel, cudaFuncAttributeMaxDynamicSharedMemorySize, CV_SMEM);
        cudaFuncSetAttribute(kgen_kernel, cudaFuncAttributeMaxDynamicSharedMemorySize, KG_SMEM);
        cudaFuncSetAttribute(a1_kernel, cudaFuncAttributeMaxDynamicSharedMemorySize, A1_SMEM);
        int dev; cudaGetDevice(&dev); cudaDeviceGetAttribute(&h_nsm, cudaDevAttrMultiProcessorCount, dev);
        if (h_nsm != 132) h_nsm = 128;
        h_tab.ns = h_nsm == 132 ? 132 : ~0u;
        for (int i = 0; i < 264; i++) {
            const int h = (i - 64) >> 1;
            const int t = i >= 132 ? i - 132 : i < 64 ? ((i >> 1) & 7) * 16 + (i >> 4) * 2 + (i & 1) : i < 120 ? (1 + h % 7) * 16 + 8 + (h / 7) * 2 + (i & 1) : i < 124 ? 128 : i - 116;
            const int hg = (4 * (t >> 6) + (t & 3)) & 7;
            h_tab.e[i] = {(unsigned char)((t >> 2) & 15), (unsigned char)hg, (unsigned char)(5 * (hg >> 2)), (unsigned char)t, (uint32_t)(hg * 10 * WQ_STAGE)};
        }
        cudaGetSymbolAddress(&h_sym[0], g_tap); cudaGetSymbolAddress(&h_sym[1], g_wq); cudaGetSymbolAddress(&h_sym[2], g_wo);
        cudaGetSymbolAddress(&h_sym[3], g_halo); cudaGetSymbolAddress(&h_sym[4], g_sum); cudaGetSymbolAddress(&h_sym[5], g_csp); cudaGetSymbolAddress(&h_sym[6], g_of);
        cudaGetSymbolAddress(&h_sym[7], g_piv); cudaGetSymbolAddress(&h_sym[8], g_x1T); cudaGetSymbolAddress(&h_sym[9], g_xcT); cudaGetSymbolAddress(&h_sym[10], g_yT);
        void *px1, *px2;
        cudaGetSymbolAddress(&px1, g_x1T); cudaGetSymbolAddress(&px2, g_xcT);
        make_tmap(&h_tmX0, d_in[0], 128 * 640, 64, 64, 64, CU_TENSOR_MAP_SWIZZLE_128B, 1280, 640, 0);
        make_tmap(&h_tmX1, px2, 128, 64 * XCP, 64, 64, CU_TENSOR_MAP_SWIZZLE_128B, XCP, 64, 0);
        make_tmap(&h_tmR0, d_in[0], 640, 1024, 80, 64, CU_TENSOR_MAP_SWIZZLE_NONE, 1280, 640, 1);
        make_tmap(&h_tmR1, px2, 64, 640, 64, 80, CU_TENSOR_MAP_SWIZZLE_128B, XCP, 64, 1);
        make_tmap(&h_tmX1st, px1, 2048, 640, 64, 80, CU_TENSOR_MAP_SWIZZLE_128B, XCP);
        make_tmap(&h_tmWq, d_in[1], 16, 640, 16, 32, CU_TENSOR_MAP_SWIZZLE_32B, 1920, 16, 5);
        make_tmap(&h_tmWo, d_in[2], 640, 640, 4, 0, CU_TENSOR_MAP_SWIZZLE_32B);
        make_tmap(&h_tmWt, d_in[2], 640, 640, 2, 0, CU_TENSOR_MAP_SWIZZLE_32B);
        make_tmap(&h_tmOut, d_out, 640, 1024, 80, 8, CU_TENSOR_MAP_SWIZZLE_NONE, 1280, 640, 1);
        p_in = d_in[0]; p_w1 = d_in[1]; p_w2 = d_in[2]; p_out = d_out;
    }
    for (int k = 0; k < n_stage_kernels(); k++) launch_stage(k, d_in, d_out);
}
```

```cpp
#include <cuda_runtime.h>
#include <cuda_bf16.h>
#include <stdint.h>
#include <cuda.h>

typedef __nv_bfloat16 bf16;

constexpr int SEQ = 2048;
constexpr int DM = 640;
constexpr int NMODE = 192;

__device__ __forceinline__ float bf2f(bf16 v) { return __bfloat162float(v); }
__device__ __forceinline__ float rbf(float v) {
    uint32_t r;
    asm("cvt.rn.bf16x2.f32 %0, %1, %2;" : "=r"(r) : "f"(v), "f"(0.f));
    return __uint_as_float(r);
}
__device__ __forceinline__ uint32_t pack2(float lo, float hi) {
    __nv_bfloat162 t = __floats2bfloat162_rn(lo, hi);
    return *reinterpret_cast<uint32_t*>(&t);
}
__device__ __forceinline__ void pdl_sync() {
    asm volatile("griddepcontrol.wait;" ::: "memory");
    asm volatile("griddepcontrol.launch_dependents;" ::: "memory");
}
__device__ __forceinline__ float sqrt_apx(float v) { float r; asm("sqrt.approx.ftz.f32 %0, %1;" : "=f"(r) : "f"(v)); return r; }
__device__ __forceinline__ float rcp_apx(float v) { float r; asm("rcp.approx.ftz.f32 %0, %1;" : "=f"(r) : "f"(v)); return r; }
__device__ __forceinline__ uint32_t smem_u32(const void* p) { return (uint32_t)__cvta_generic_to_shared(p); }

constexpr int TAPB = 2 * 152 * 8;
__device__ __align__(128) uint4 g_tap[DM * 128];
#define XPAD 64
constexpr int XCP = SEQ + XPAD;
__device__ __align__(128) bf16 g_x1T[DM * XCP];
__device__ __align__(128) bf16 g_xcT[DM * XCP];
__device__ __align__(128) uint4 g_of[128 * 1280];
constexpr int WQ_STAGE = 240 * 128, WOB = 80 * 160;
__device__ __align__(128) uint4 g_wq[8 * 10 * WQ_STAGE / 16];
__device__ __align__(128) uint4 g_wo[64 * WOB / 16];
__device__ __align__(16) float g_csp[10 * 1920];
#define FSTR 32
__device__ __align__(128) float2 g_sum[2 * SEQ + 256 * FSTR];
__device__ __align__(16) bf16 g_piv[2 * SEQ];
__device__ __align__(128) bf16 g_yT[DM * XCP];
__device__ uint32_t g_epoch;
__device__ __align__(16) unsigned long long g_rstat[SEQ];
__device__ __align__(128) uint4 g_halo[640 * 148];
__device__ __forceinline__ unsigned long long tagw(uint32_t payload, uint32_t tag) { return ((unsigned long long)tag << 32) | payload; }
__device__ __forceinline__ ulonglong2 ld_tag2(const ulonglong2* p) {
    ulonglong2 v;
    asm volatile("ld.relaxed.gpu.global.v2.u64 {%0, %1}, [%2];" : "=l"(v.x), "=l"(v.y) : "l"(p) : "memory");
    return v;
}
__device__ __forceinline__ bool tag_ok(ulonglong2 v, uint32_t tag) { return (uint32_t)(v.x >> 32) == tag && (uint32_t)(v.y >> 32) == tag; }
__device__ __forceinline__ uint32_t ld_epoch() { uint32_t v; asm volatile("ld.relaxed.gpu.global.u32 %0, [%1];" : "=r"(v) : "l"(&g_epoch) : "memory"); return v + 1; }
constexpr int SPIN_MAX = 1 << 20;
__device__ uint32_t g_started[4];
__device__ __forceinline__ void sm_started(int slot) { asm volatile("red.relaxed.gpu.global.add.u32 [%0], 1;" ::"l"(g_started + slot) : "memory"); }
__device__ __noinline__ void sm_idle(int slot) {
    if (threadIdx.x) return;
    sm_started(slot);
    const uint32_t want = ld_epoch() * gridDim.x;
    pdl_sync();
#pragma unroll 1
    for (int it = 0; it < SPIN_MAX; it++) {
        uint32_t v;
        asm volatile("ld.relaxed.gpu.global.u32 %0, [%1];" : "=r"(v) : "l"(g_started + slot) : "memory");
        if ((int)(v - want) >= 0) break;
        __nanosleep(100);
    }
}
struct TileTab { uint32_t ns, pad; struct { unsigned char mb, hg, kb0, tile; uint32_t woff; } __align__(8) e[264]; };
__device__ __forceinline__ bool elect() {
    uint32_t p;
    asm volatile("{\n.reg .pred p;\nelect.sync _|p, 0xffffffff;\nselp.b32 %0, 1, 0, p;\n}" : "=r"(p));
    return p;
}
#define DBG_SYMS
#define TSTAMP(i)
#define TSTAMP1(i)
#define TSTAMP1T(i, t)
#define TSTAMP1X(i, t)
#define SPAN(k, i)
#define GSTAMP(arr, i)
#define TSTAMP2(i)
#define TSTAMP3(i)
#define TSTAMP4(i)
#define TSTAMPK(i, t)
#define TSTAMPC(i)
#define DBGC(i)
#define DBGV(i, v)
#define DBGCAL(i)

#define CSA(i)
#define CSA_END
#define CST(i)
#define CST_END
#define CST_EXTRA 0
__device__ __forceinline__ void mma_bf16(float* d, uint32_t a0, uint32_t a1, uint32_t a2, uint32_t a3, uint32_t b0, uint32_t b1) {
    asm volatile("mma.sync.aligned.m16n8k16.row.col.f32.bf16.bf16.f32 {%0,%1,%2,%3}, {%4,%5,%6,%7}, {%8,%9}, {%0,%1,%2,%3};"
                 : "+f"(d[0]), "+f"(d[1]), "+f"(d[2]), "+f"(d[3]) : "r"(a0), "r"(a1), "r"(a2), "r"(a3), "r"(b0), "r"(b1));
}
__device__ __forceinline__ void mma_bf16_k8(float* d, uint32_t a0, uint32_t a1, uint32_t b0) {
    asm volatile("mma.sync.aligned.m16n8k8.row.col.f32.bf16.bf16.f32 {%0,%1,%2,%3}, {%4,%5}, {%6}, {%0,%1,%2,%3};"
                 : "+f"(d[0]), "+f"(d[1]), "+f"(d[2]), "+f"(d[3]) : "r"(a0), "r"(a1), "r"(b0));
}
__device__ __forceinline__ void ldsm_x4(uint32_t* r, uint32_t addr) {
    asm volatile("ldmatrix.sync.aligned.m8n8.x4.shared.b16 {%0,%1,%2,%3}, [%4];"
                 : "=r"(r[0]), "=r"(r[1]), "=r"(r[2]), "=r"(r[3]) : "r"(addr));
}

__device__ __forceinline__ void ldsm_x4_t(uint32_t* r, uint32_t addr) {
    asm volatile("ldmatrix.sync.aligned.m8n8.x4.trans.shared.b16 {%0,%1,%2,%3}, [%4];"
                 : "=r"(r[0]), "=r"(r[1]), "=r"(r[2]), "=r"(r[3]) : "r"(addr));
}
__device__ __forceinline__ void mbar_init(uint32_t bar, int count) { asm volatile("mbarrier.init.shared::cta.b64 [%0], %1;" ::"r"(bar), "r"(count)); }
__device__ __forceinline__ void mbar_arrive(uint32_t bar) { asm volatile("mbarrier.arrive.shared::cta.b64 _, [%0];" ::"r"(bar) : "memory"); }
__device__ __forceinline__ void mbar_wait(uint32_t bar, uint32_t parity) {
    asm volatile("{\n.reg .pred p;\nWAIT_LOOP:\n"
                 "mbarrier.try_wait.parity.shared::cta.b64 p, [%0], %1;\n"
                 "@p bra.uni WAIT_DONE;\nbra.uni WAIT_LOOP;\nWAIT_DONE:\n}" ::"r"(bar), "r"(parity) : "memory");
}

__device__ __forceinline__ void mbar_expect_tx(uint32_t bar, uint32_t bytes) {
    asm volatile("mbarrier.arrive.expect_tx.shared::cta.b64 _, [%0], %1;" ::"r"(bar), "r"(bytes) : "memory");
}
__device__ __forceinline__ void tma_load_2d(uint32_t dst, const void* tmap, int c0, int c1, uint32_t bar) {
    asm volatile("cp.async.bulk.tensor.2d.shared::cluster.global.mbarrier::complete_tx::bytes [%0], [%1, {%3, %4}], [%2];"
                 ::"r"(dst), "l"(tmap), "r"(bar), "r"(c0), "r"(c1) : "memory");
}
__device__ __forceinline__ void tma_load_3d(uint32_t dst, const void* tmap, int c0, int c1, int c2, uint32_t bar) {
    asm volatile("cp.async.bulk.tensor.3d.shared::cluster.global.mbarrier::complete_tx::bytes [%0], [%1, {%3, %4, %5}], [%2];"
                 ::"r"(dst), "l"(tmap), "r"(bar), "r"(c0), "r"(c1), "r"(c2) : "memory");
}
__device__ __forceinline__ void fence_async_smem() { asm volatile("fence.proxy.async.shared::cta;" ::: "memory"); }
__device__ __forceinline__ void bulk_load(uint32_t dst, const void* src, uint32_t bytes, uint32_t bar) {
    asm volatile("cp.async.bulk.shared::cluster.global.mbarrier::complete_tx::bytes [%0], [%1], %2, [%3];"
                 ::"r"(dst), "l"(src), "r"(bytes), "r"(bar) : "memory");
}
__device__ __forceinline__ void stsm_x4(uint32_t addr, uint32_t r0, uint32_t r1, uint32_t r2, uint32_t r3) {
    asm volatile("stmatrix.sync.aligned.m8n8.x4.shared.b16 [%0], {%1,%2,%3,%4};" ::"r"(addr), "r"(r0), "r"(r1), "r"(r2), "r"(r3) : "memory");
}
__device__ __forceinline__ void stsm_x4_t(uint32_t addr, uint32_t r0, uint32_t r1, uint32_t r2, uint32_t r3) {
    asm volatile("stmatrix.sync.aligned.m8n8.x4.trans.shared.b16 [%0], {%1,%2,%3,%4};" ::"r"(addr), "r"(r0), "r"(r1), "r"(r2), "r"(r3) : "memory");
}
__device__ __forceinline__ void prefetch_tmap(const void* tmap) { asm volatile("prefetch.tensormap [%0];" ::"l"(tmap) : "memory"); }

__device__ __forceinline__ float2 cexp_at(float wr2, float wi, float p) {
    float er;
    asm("ex2.approx.ftz.f32 %0, %1;" : "=f"(er) : "f"(wr2 * p));
    float th = wi * p;
    const float k = rintf(th * 0.15915494309189535f);
    th = fmaf(k, -6.2831854820251465f, th);
    th = fmaf(k, 1.7484555314695172e-7f, th);
    return make_float2(er * __cosf(th), er * __sinf(th));
}
__device__ __forceinline__ float2 cmul(float2 a, float2 b) {
    return make_float2(fmaf(a.x, b.x, -a.y * b.y), fmaf(a.x, b.y, a.y * b.x));
}
__device__ __forceinline__ float2 csqr(float2 a) { return make_float2(fmaf(a.x, a.x, -a.y * a.y), (a.x + a.x) * a.y); }
__device__ __forceinline__ uint32_t packh(float2 v) {
    uint32_t r;
    asm("cvt.rn.f16x2.f32 %0, %1, %2;" : "=r"(r) : "f"(v.y), "f"(v.x));
    return r;
}
__device__ __forceinline__ void mma_f16(float* d, uint32_t a0, uint32_t a1, uint32_t a2, uint32_t a3, uint32_t b0, uint32_t b1) {
    asm volatile("mma.sync.aligned.m16n8k16.row.col.f32.f16.f16.f32 {%0,%1,%2,%3}, {%4,%5,%6,%7}, {%8,%9}, {%0,%1,%2,%3};"
                 : "+f"(d[0]), "+f"(d[1]), "+f"(d[2]), "+f"(d[3]) : "r"(a0), "r"(a1), "r"(a2), "r"(a3), "r"(b0), "r"(b1));
}

struct KgIn { const bf16 *logA, *Aim, *Cre, *Cim, *logdt, *dsk, *x, *wqkv, *wo; uint4 *tap, *wq, *wop, *halo, *sum; float* csp; };
constexpr int KG_THREADS = NMODE / 2;

constexpr int KG_BUF = 15 * 12288, KG_BAR = KG_BUF + 6 * 5120, KG_SMEM = KG_BAR + 64;
__global__ void __launch_bounds__(512, 1) kgen_kernel(const KgIn in, const __grid_constant__ CUtensorMap tmWq, const __grid_constant__ CUtensorMap tmWo,
                                                        const __grid_constant__ CUtensorMap tmWt) {
    extern __shared__ __align__(1024) uint4 tabs[];
#define KG_ROT 0
    const int lane = threadIdx.x & 31, w16 = (__shfl_sync(~0u, threadIdx.x >> 5, 0) + KG_ROT) & 15, grp = w16 / 3, warp = w16 - 3 * grp;
    const int d = blockIdx.x * 5 + grp, tid = warp * 32 + lane;
    uint4* tab = tabs + grp * (3 * 768);
    SPAN(0, 0); SPAN(0, 1);
    TSTAMPK(0, 0);
    asm volatile("griddepcontrol.launch_dependents;" ::: "memory");
    if (w16 == 15) {
        const uint32_t b0 = smem_u32(tab), wbar = b0 + 6 * 5120;
        const int blk = blockIdx.x, nq = blk < 112 ? 4 : 2, nj = nq + (blk < 64 ? 1 : 2);
        auto fetch = [&](int i) {
            const uint32_t dst = b0 + i * 5120, bar = wbar + 8 * i;
            if (i < nq) {
                const int p = blk + 64 * (i & 2), kb = p / 24;
                mbar_expect_tx(bar, 5120);
                tma_load_3d(dst, &tmWq, 0, kb * 64 + (i & 1) * 32, (p - 24 * kb) * 5, bar);
            } else if (i < nj) {
                const int o = i == nq ? blk : 255 - blk;
                mbar_expect_tx(bar, o < 128 ? 5120 : 2560);
                asm volatile("cp.async.bulk.tensor.5d.shared::cluster.global.mbarrier::complete_tx::bytes [%0], [%1, {%3, %3, %4, %3, %5}], [%2];"
                             ::"r"(dst), "l"(o < 128 ? &tmWo : &tmWt), "r"(bar), "r"(0), "r"((o & 7) * 10 + (o >> 6) * 4), "r"(((o >> 3) & 7) * 5) : "memory");
            }
        };
        const bool one = elect();
        if (one) {
#pragma unroll
            for (int i = 0; i < 6; i++) mbar_init(wbar + 8 * i, 1);
            asm volatile("fence.mbarrier_init.release.cluster;" ::: "memory");
#pragma unroll
            for (int i = 0; i < 6; i++) fetch(i);
        }
        __syncwarp();
#pragma unroll
        for (int i = 1; i <= 5; i++) asm volatile("bar.arrive %0, 128;" ::"r"(i) : "memory");
        if (one) {
#pragma unroll 1
            for (int i = 0; i < nj; i++) {
                const int p = blk + 64 * (i & 2), kb = p / 24, hg = p & 7, sec = (p - 24 * kb) >> 3, o = i == nq ? blk : 255 - blk, cg = (o >> 3) & 7, hb = o & 7;
                const unsigned char* dst = i < nq ? reinterpret_cast<unsigned char*>(in.wq) + (hg * 10 + (hg < 4 ? kb : kb < 5 ? kb + 5 : kb - 5)) * WQ_STAGE + ((i & 1) * 3 + sec) * 5120
                                                  : reinterpret_cast<unsigned char*>(in.wop) + (cg * 8 + (hb == cg ? 0 : hb + (hb < cg))) * WOB + (o >> 6) * 5120;
                mbar_wait(wbar + 8 * i, 0);
                if (i == 0) TSTAMPK(2, (15 - KG_ROT) * 32);
                if (i == 3) TSTAMPK(5, (15 - KG_ROT) * 32);
                asm volatile("cp.async.bulk.global.shared::cta.bulk_group [%0], [%1], %2;" ::"l"(dst), "r"(b0 + i * 5120), "r"(i < nq || o < 128 ? 5120 : 2560) : "memory");
            }
            asm volatile("cp.async.bulk.commit_group;" ::: "memory");
            asm volatile("cp.async.bulk.wait_group.read 0;" ::: "memory");
        }
        TSTAMPK(11, (15 - KG_ROT) * 32);
        return;
    }
    const bf16 pdt = in.logdt[d], pdsk = in.dsk[d];
    const uint32_t pla = reinterpret_cast<const uint32_t*>(in.logA)[d * KG_THREADS + tid], pai = reinterpret_cast<const uint32_t*>(in.Aim)[d * KG_THREADS + tid];
    const uint32_t pcr = reinterpret_cast<const uint32_t*>(in.Cre)[d * KG_THREADS + tid], pci = reinterpret_cast<const uint32_t*>(in.Cim)[d * KG_THREADS + tid];
    const bf16* pfq = tid < 30 ? in.wqkv + (size_t)(d * 30 + tid) * 64 : tid < 40 ? in.wo + (size_t)(d * 10 + tid - 30) * 64 : in.x + (size_t)(d * 32 + tid - 40) * 64;
#define KG_PF 0
    if (tid < (KG_PF == 3 ? 0 : KG_PF ? 40 : 72)) asm volatile("prefetch.global.L2 [%0];" ::"l"(pfq));
    asm volatile("st.global.v4.u32 [%0], {%1,%1,%1,%1};" ::"l"(in.halo + d * 148 + tid), "r"(~0u));
    if (tid < 52) asm volatile("st.global.v4.u32 [%0], {%1,%1,%1,%1};" ::"l"(in.halo + d * 148 + 96 + tid), "r"(~0u));
    else if (w16 == 2) {
        if (lane < 16) in.sum[blockIdx.x * 16 + lane] = make_uint4(0, 0, 0, 0);
        else if (lane < 20) reinterpret_cast<uint32_t*>(in.sum + 2048)[(blockIdx.x * 4 + lane - 16) * FSTR] = 0;
    }
    const uint32_t tw = smem_u32(tab) + warp * 12288;
    const int g = lane >> 2, t = lane & 3;
    const uint32_t sta = tw + lane * 128 + ((2 * (lane & 3) + ((lane >> 2) & 1)) << 4);
    const uint32_t lda = tw + t * 128 + ((g ^ (2 * t)) << 4);
    const uint32_t stb = tw + lane * 8, ldb = tw + g * 512 + (g & 3) * 32 + t * 8;
    auto sts4 = [&](int e, int off, uint32_t a, uint32_t b, uint32_t c, uint32_t dd) {
        asm volatile("st.shared.v4.u32 [%0], {%1,%2,%3,%4};" ::"r"((sta ^ (e << 4)) + off), "r"(a), "r"(b), "r"(c), "r"(dd) : "memory");
    };
    auto lds4 = [&](int sp, int off, uint32_t* r) {
        asm volatile("ld.shared.v4.u32 {%0,%1,%2,%3}, [%4];" : "=r"(r[0]), "=r"(r[1]), "=r"(r[2]), "=r"(r[3]) : "r"((lda ^ ((sp & 1) << 4)) + sp * 512 + off) : "memory");
    };
    const float dt = rbf(expf(bf2f(pdt)));
    float2 C[2], y1[2], z8[2], y128[2];
    float cmax = 0.f;
#pragma unroll
    for (int m = 0; m < 2; m++) {
        const float wr2 = -rbf(expf(__uint_as_float(m ? pla & 0xffff0000u : pla << 16))) * dt * 1.4426950408889634f;
        const float wi = __uint_as_float(m ? pai & 0xffff0000u : pai << 16) * dt;
        C[m] = make_float2(__uint_as_float(m ? pcr & 0xffff0000u : pcr << 16) * dt, -__uint_as_float(m ? pci & 0xffff0000u : pci << 16) * dt);
        cmax = fmaxf(cmax, fmaxf(fabsf(C[m].x), fabsf(C[m].y)));
        y1[m] = cexp_at(wr2, -wi, 1.f); z8[m] = cexp_at(wr2, wi, 8.f); y128[m] = cexp_at(wr2, -wi, 128.f);
    }
    const int ex = min(max((int)(__reduce_max_sync(~0u, __float_as_uint(cmax)) >> 23), 20), 240);
    const float scale = __uint_as_float((uint32_t)(127 + 10 + 127 - ex) << 23), unscale = 2.0f * __uint_as_float((uint32_t)(ex - 10) << 23);
    TSTAMPK(4, 64);
    if (KG_PF >= 2 && tid >= 40 && tid < 72) asm volatile("prefetch.global.L2 [%0];" ::"l"(pfq));
    float k2048 = 0.f;
    float acc[5][4];
#pragma unroll
    for (int j = 0; j < 5; j++)
#pragma unroll
        for (int k = 0; k < 4; k++) acc[j][k] = 0.f;
    uint32_t af[8][4];
    {
        float2 h0[2], h1[2], g0[2], g1[2], g2[2], g2b[2], g3[2], g4[2], y2[2], y4[2];
#pragma unroll
        for (int m = 0; m < 2; m++) {
            h0[m] = make_float2(1.f, 0.f); h1[m] = csqr(csqr(csqr(z8[m])));
            g0[m] = make_float2(C[m].x * scale, C[m].y * scale);
            g1[m] = cmul(g0[m], y128[m]);
            const float2 y256 = csqr(y128[m]), y512 = csqr(y256);
            g2b[m] = g2[m] = cmul(g0[m], y256); g3[m] = cmul(g0[m], y512); g4[m] = cmul(g3[m], y512);
            y2[m] = csqr(y1[m]); y4[m] = csqr(y2[m]);
            const float2 y1024 = csqr(y512);
            k2048 += fmaf(g4[m].x, y1024.x, -g4[m].y * y1024.y);
        }
#pragma unroll
        for (int e = 0; e < 8; e++) {
            sts4(e, 0, packh(h0[0]), packh(h1[0]), packh(h0[1]), packh(h1[1]));
            sts4(e, 4096, packh(g0[0]), packh(g0[1]), packh(g1[0]), packh(g1[1]));
#pragma unroll
            for (int m = 0; m < 2; m++)
                if (e < 7) { h0[m] = e ? cmul(h0[m], z8[m]) : z8[m]; h1[m] = cmul(h1[m], z8[m]); g0[m] = cmul(g0[m], y1[m]); g1[m] = cmul(g1[m], y1[m]); }
            if (e < 5) k2048 += __shfl_xor_sync(~0u, k2048, 1 << e);
        }
        if (KG_PF == 1 && tid >= 40 && tid < 72) asm volatile("prefetch.global.L2 [%0];" ::"l"(pfq));
        __syncwarp();
#pragma unroll
        for (int e = 0; e < 8; e++) {
            uint32_t b[4];
            lds4(e, 0, af[e]); lds4(e, 4096, b);
            sts4(e, 8192, packh(g2[0]), packh(g2[1]), packh((e & 1) ? cmul(g3[0], y4[0]) : g3[0]), packh((e & 1) ? cmul(g3[1], y4[1]) : g3[1]));
            asm volatile("st.shared.v2.u32 [%0], {%1,%2};" ::"r"((stb ^ ((e & 3) << 5)) + e * 512), "r"(packh(g4[0])), "r"(packh(g4[1])) : "memory");
#pragma unroll
            for (int m = 0; m < 2; m++)
                if (e < 7) {
                    g2[m] = e == 3 ? cmul(g2b[m], y128[m]) : cmul(g2[m], y2[m]);
                    if (e & 1) g3[m] = cmul(g3[m], y128[m]);
                    g4[m] = cmul(g4[m], y128[m]);
                }
            mma_f16(acc[0], af[e][0], af[e][1], af[e][2], af[e][3], b[0], b[1]);
            mma_f16(acc[1], af[e][0], af[e][1], af[e][2], af[e][3], b[2], b[3]);
        }
    }
    TSTAMPK(6, 64);
    __syncwarp();
#pragma unroll
    for (int sp = 0; sp < 8; sp++) {
        uint32_t c[4], e0, e1;
        lds4(sp, 8192, c);
        asm volatile("ld.shared.v2.u32 {%0,%1}, [%2];" : "=r"(e0), "=r"(e1) : "r"(ldb ^ (sp << 5)) : "memory");
        mma_f16(acc[2], af[sp][0], af[sp][1], af[sp][2], af[sp][3], c[0], c[1]);
        mma_f16(acc[3], af[sp][0], af[sp][1], af[sp][2], af[sp][3], c[2], c[3]);
        mma_f16(acc[4], af[sp][0], af[sp][1], af[sp][2], af[sp][3], e0, e1);
    }
    {
        float* Pp = reinterpret_cast<float*>(tab + warp * 768);
        auto sw = [](int i) { return i ^ ((i >> 2) & 24); };
#pragma unroll
        for (int h = 0; h < 2; h++) {
            const int b = g + 8 * h;
            *reinterpret_cast<float2*>(Pp + sw(8 * b + 2 * t)) = make_float2(acc[0][2 * h] * unscale, acc[0][2 * h + 1] * unscale);
            *reinterpret_cast<float2*>(Pp + 128 + sw(8 * b + 2 * t)) = make_float2(acc[1][2 * h] * unscale, acc[1][2 * h + 1] * unscale);
            *reinterpret_cast<float2*>(Pp + 256 + sw(4 * b + 2 * (t & 1) + 64 * (t >> 1))) = make_float2(acc[2][2 * h] * unscale, acc[2][2 * h + 1] * unscale);
            *reinterpret_cast<float2*>(Pp + 384 + sw(2 * b + 32 * t)) = make_float2(acc[3][2 * h] * unscale, acc[3][2 * h + 1] * unscale);
            Pp[512 + sw(b + 32 * t)] = acc[4][2 * h] * unscale;
            Pp[512 + sw(b + 32 * t + 16)] = acc[4][2 * h + 1] * unscale;
        }
        if (lane == 0) Pp[640] = k2048 * unscale;
    }
    TSTAMPK(7, 64);
    asm volatile("bar.sync %0, 128;" ::"r"(grp + 1) : "memory");
    TSTAMPK(9, 64);
    const float* Kp = reinterpret_cast<const float*>(tab);
    auto ksum = [&](int i) -> float { return (Kp[i] + Kp[3072 + i]) + Kp[6144 + i]; };
    auto ksum4 = [&](int q) -> float4 {
        q ^= (q >> 2) & 6;
        const float4 a = reinterpret_cast<const float4*>(Kp)[q], b = reinterpret_cast<const float4*>(Kp)[768 + q], c = reinterpret_cast<const float4*>(Kp)[1536 + q];
        return make_float4((a.x + b.x) + c.x, (a.y + b.y) + c.y, (a.z + b.z) + c.z, (a.w + b.w) + c.w);
    };
    {
        uint2* E4 = reinterpret_cast<uint2*>(in.tap + d * 128);
        float4 v = ksum4(tid), u = ksum4(96 + min(tid, 64));
        const float cor = rbf(ksum(tid == 95 ? 384 : 512));
        if (tid == 0) v.x += bf2f(pdsk);
        if (tid == 95) v.w -= cor;
        if (tid == 31) u.w -= cor;
        const uint32_t lo = pack2(v.x, v.y), hi = pack2(v.z, v.w);
        if (tid < 64) {
            E4[6 + tid] = make_uint2(lo, hi);
            E4[(tid < 32 ? 159 : 209 - 32) + tid] = make_uint2(pack2(u.x, u.y), pack2(u.z, u.w));
        } else {
            const uint32_t nx = __shfl_down_sync(~0u, lo, 1);
            in.tap[d * 128 + 35 + tid - 64] = make_uint4(__byte_perm(lo, 0, 0x1010), __byte_perm(lo, hi, 0x5432), __byte_perm(hi, 0, 0x1010), __byte_perm(hi, tid == 95 ? 0u : nx, 0x5432));
            if (tid == 64) E4[241] = make_uint2(pack2(u.x, 0.f), 0u);
        }
    }
    TSTAMPK(10, 64);
    if (warp < (blockIdx.x < 112 ? 2 : 1)) {
        const uint32_t sb = smem_u32(tabs);
        mbar_wait(sb + KG_BAR + 16 * warp, 0); mbar_wait(sb + KG_BAR + 16 * warp + 8, 0);
        uint32_t w[4][4];
        float cs[4] = {0.f, 0.f, 0.f, 0.f};
#pragma unroll
        for (int a = 0; a < 4; a++)
            ldsm_x4_t(w[a], sb + KG_BUF + warp * 10240 + grp * 1024 + ((lane >> 4) * 8 + (lane & 7)) * 32 + ((((lane >> 3) ^ (lane >> 2)) & 1) << 4) + (a >> 1) * 5120 + (a & 1) * 512);
#pragma unroll
        for (int a = 0; a < 4; a++) mma_bf16(cs, w[a][0], w[a][1], w[a][2], w[a][3], 0x3f803f80u, 0x3f803f80u);
        if (t < 2) in.csp[(blockIdx.x + 128 * warp) * 80 + grp * 16 + g + 8 * t] = t ? cs[2] : cs[0];
    }
    SPAN(0, 3);
}

#define CV_SLEEP 40
#define CV_D2 3
#define CV_PDH 12
#define CV_PDF 4
#define CV_HAND 7
constexpr int CV_CPB = 5;
constexpr int CV_THREADS = 512;
constexpr int UPADF = 128;
constexpr int ULEN = UPADF + SEQ;
constexpr int XLEN = SEQ + 16;
constexpr int BX_5 = 0, BX_3 = 3264, BX_9 = 6528, BX_7 = 8960, BX_LEN = 11392;
constexpr int CV_SM_U = 0;
constexpr int CV_SM_T = CV_CPB * ULEN * 2;
constexpr int CV_SM_B = CV_SM_T + CV_CPB * TAPB;
constexpr int CV_SM_X = CV_SM_B + CV_CPB * BX_LEN;
constexpr int CV_SM_Y = (CV_SM_X + CV_CPB * XLEN * 2 + 127) & ~127;
constexpr int CV_SM_CNT = CV_SM_Y + CV_CPB * 8192;
constexpr int CV_SM_O = CV_SM_CNT + 128;
constexpr int CV_SMEM = CV_SM_O + 20480 + CST_EXTRA;
static_assert(ULEN % 128 == 0 && CV_SM_B % 128 == 0 && CV_SM_CNT % 128 == 0, "layout");

__device__ __forceinline__ uint32_t sub2(uint32_t x, uint32_t m) {
    const __nv_bfloat162 d = __hsub2(*reinterpret_cast<const __nv_bfloat162*>(&x), *reinterpret_cast<const __nv_bfloat162*>(&m));
    return *reinterpret_cast<const uint32_t*>(&d);
}
__device__ __forceinline__ uint32_t add2(uint32_t x, uint32_t y) {
    const __nv_bfloat162 d = __hadd2_rn(*reinterpret_cast<const __nv_bfloat162*>(&x), *reinterpret_cast<const __nv_bfloat162*>(&y));
    return *reinterpret_cast<const uint32_t*>(&d);
}
__device__ __forceinline__ void wgmma_fence() { asm volatile("wgmma.fence.sync.aligned;" ::: "memory"); }
__device__ __forceinline__ void wgmma_commit() { asm volatile("wgmma.commit_group.sync.aligned;" ::: "memory"); }
template <int N> __device__ __forceinline__ void wgmma_wait() { asm volatile("wgmma.wait_group.sync.aligned %0;" ::"n"(N) : "memory"); }
__device__ __forceinline__ uint64_t make_desc(uint32_t addr, uint32_t lbo, uint32_t sbo, uint32_t mode) {
    return (uint64_t)((addr & 0x3FFFF) >> 4) | ((uint64_t)(lbo >> 4) << 16) | ((uint64_t)(sbo >> 4) << 32) | ((uint64_t)mode << 62);
}
__device__ __forceinline__ void wgmma_rs128(float (&d)[64], uint2 hi, uint2 lo, uint64_t db, int acc) {
    asm volatile("{\n.reg .pred p;\nsetp.ne.b32 p, %69, 0;\nwgmma.mma_async.sync.aligned.m64n128k16.f32.bf16.bf16 {%0,%1,%2,%3,%4,%5,%6,%7,%8,%9,%10,%11,%12,%13,%14,%15,%16,%17,%18,%19,%20,%21,%22,%23,%24,%25,%26,%27,%28,%29,%30,%31,%32,%33,%34,%35,%36,%37,%38,%39,%40,%41,%42,%43,%44,%45,%46,%47,%48,%49,%50,%51,%52,%53,%54,%55,%56,%57,%58,%59,%60,%61,%62,%63}, {%64,%65,%66,%67}, %68, p, 1, 1, 0;\n}"
                 : "+f"(d[0]), "+f"(d[1]), "+f"(d[2]), "+f"(d[3]), "+f"(d[4]), "+f"(d[5]), "+f"(d[6]), "+f"(d[7]), "+f"(d[8]), "+f"(d[9]), "+f"(d[10]), "+f"(d[11]), "+f"(d[12]), "+f"(d[13]), "+f"(d[14]), "+f"(d[15]), "+f"(d[16]), "+f"(d[17]), "+f"(d[18]), "+f"(d[19]), "+f"(d[20]), "+f"(d[21]), "+f"(d[22]), "+f"(d[23]), "+f"(d[24]), "+f"(d[25]), "+f"(d[26]), "+f"(d[27]), "+f"(d[28]), "+f"(d[29]), "+f"(d[30]), "+f"(d[31]), "+f"(d[32]), "+f"(d[33]), "+f"(d[34]), "+f"(d[35]), "+f"(d[36]), "+f"(d[37]), "+f"(d[38]), "+f"(d[39]), "+f"(d[40]), "+f"(d[41]), "+f"(d[42]), "+f"(d[43]), "+f"(d[44]), "+f"(d[45]), "+f"(d[46]), "+f"(d[47]), "+f"(d[48]), "+f"(d[49]), "+f"(d[50]), "+f"(d[51]), "+f"(d[52]), "+f"(d[53]), "+f"(d[54]), "+f"(d[55]), "+f"(d[56]), "+f"(d[57]), "+f"(d[58]), "+f"(d[59]), "+f"(d[60]), "+f"(d[61]), "+f"(d[62]), "+f"(d[63])
                 : "r"(hi.x), "r"(hi.y), "r"(lo.x), "r"(lo.y), "l"(db), "r"(acc));
}
template <int V> struct Int { __device__ constexpr operator int() const { return V; } };
__device__ __forceinline__ void sts4(uint32_t a, const uint32_t* v) { asm volatile("st.shared.v4.u32 [%0], {%1,%2,%3,%4};" ::"r"(a), "r"(v[0]), "r"(v[1]), "r"(v[2]), "r"(v[3]) : "memory"); }
__device__ __forceinline__ uint32_t lds1(uint32_t a) { uint32_t v; asm volatile("ld.shared.u32 %0, [%1];" : "=r"(v) : "r"(a) : "memory"); return v; }
__device__ __forceinline__ uint4 lds4(uint32_t a) { uint4 v; asm volatile("ld.shared.v4.u32 {%0,%1,%2,%3}, [%4];" : "=r"(v.x), "=r"(v.y), "=r"(v.z), "=r"(v.w) : "r"(a) : "memory"); return v; }
__device__ __forceinline__ void cv_store(unsigned char* p, uint4 x, uint4 y) {
    asm volatile("st.relaxed.gpu.global.v2.u32 [%0], {%1,%2};" ::"l"(p), "r"(add2(x.x, __byte_perm(y.x, y.y, 0x5410))), "r"(add2(x.y, __byte_perm(y.z, y.w, 0x5410))) : "memory");
    asm volatile("st.relaxed.gpu.global.v2.u32 [%0], {%1,%2};" ::"l"(p + 128), "r"(add2(x.z, __byte_perm(y.x, y.y, 0x7632))), "r"(add2(x.w, __byte_perm(y.z, y.w, 0x7632))) : "memory");
}
__device__ __forceinline__ int usw(int ch) { return ch ^ ((ch >> 3) & 1); }
__global__ void __launch_bounds__(CV_THREADS, 1) conv_kernel(int layer, const uint4* __restrict__ piv, const float4* __restrict__ sum, const bf16* __restrict__ x1T,
                                                             bf16* __restrict__ dst, const uint4* __restrict__ tap, const __grid_constant__ CUtensorMap tmOut) {
    extern __shared__ __align__(1024) unsigned char sm[];
    SPAN(3 + 4 * layer, 0);
    bf16* Us = reinterpret_cast<bf16*>(sm + CV_SM_U);
    bf16* Xs = reinterpret_cast<bf16*>(sm + CV_SM_X);
#define CV_IDX int tid; asm volatile("mov.u32 %0, %tid.x;" : "=r"(tid)); const int lane = tid & 31, warp = __shfl_sync(~0u, tid >> 5, 0);
    const int d0 = blockIdx.x * CV_CPB, tile = blockIdx.x; (void)tile;
    const uint32_t cnt = smem_u32(sm + CV_SM_CNT);
    struct Lc { uint32_t a4, a8, uc, ud, y, e4, en, sp, ss; int go; };
    auto lane_consts = [&](int lane, int c) {
        const int mat = lane >> 3, r = lane & 7, g = lane >> 2, ti = lane & 3, e = g - 2 * ti;
        const int j2 = 13 + (r ^ 1) + 8 * (mat >> 1), j3 = j2 + 2, i0 = 8 * (mat & 1);
        const uint32_t sb = smem_u32(sm), oc = sb + usw(16 * (mat >> 1) + 2 * r + (mat & 1)) * 16;
        const Lc l = {sb + CV_SM_B + c * BX_LEN + ((j2 & 1) ? BX_3 + (4 * j2 + i0 + 84) * 2 : BX_5 + (4 * j2 + i0 + 80) * 2),
                      sb + CV_SM_B + c * BX_LEN + ((j3 & 1) ? BX_7 : BX_9) + (8 * j3 + i0 + 136) * 2,
                      oc + CV_SM_U + (c * ULEN + UPADF) * 2, sb + CV_SM_U + (c * ULEN + UPADF) * 2 + usw(16 * mat + 2 * r + 2) * 16, oc + CV_SM_Y + c * 8192,
                      sb + CV_SM_O + 2048 * c + (307 + 2 * g - ti) * 4, sb + CV_SM_T + c * TAPB + (152 + 144 + e) * 8 + 4,
                      e == -5 ? 0x4410u : e == -4 ? 0x1044u : 0x4444u, e == 3 ? 0x4410u : e == 4 ? 0x1044u : 0x4444u,
                      c * XCP * 2 + (lane >> 4) * 256 + (lane & 15) * 8};
        asm volatile("st.shared.u32 [%0], %1;" ::"r"(l.y), "r"(l.a4 ^ l.a8 ^ l.uc ^ l.ud ^ l.e4 ^ l.en ^ l.sp ^ l.ss ^ l.go) : "memory");
        return l;
    };
    unsigned char* const dq = reinterpret_cast<unsigned char*>(dst + (size_t)d0 * XCP);
    auto far = [&](auto T0_, const auto& seq, const Lc& lc, int c, int lane, const uint2 (&f)[20], uint32_t kk) {
        constexpr int T0 = T0_, T1 = T0 + 6, TC = T0 > 7 ? T0 : 7, NS = sizeof(seq) / sizeof(seq[0]), PD = T0 > 7 ? CV_PDH : CV_PDF;
        uint32_t bq[28], yw[4], yz[4], P, S;
        uint4 xv, yv;
        asm("prmt.b32 %0, %1, 0, %2;" : "=r"(P) : "r"(kk), "r"(lc.sp));
        asm("prmt.b32 %0, %1, 0, %2;" : "=r"(S) : "r"(kk), "r"(lc.ss));
#pragma unroll
        for (int k = 0; 2 * k < T1 - TC + 4; k++) ldsm_x4(bq + 4 * k, lc.uc + (TC - 8) * 256 + 512 * k);
#pragma unroll
        for (int k = 0; 4 * k < T1 - TC; k++) ldsm_x4(bq + 20 + 4 * k, lc.ud + (TC - 8) * 256 + 1024 * k);
        CST(3);
        mbar_wait(cnt + 8 * c, 0);
        mbar_wait(cnt + 40, 0);
        CST(4);
        float acc[6][4] = {};
        uint32_t a[PD + 1][4];
#pragma unroll
        for (int i = -PD; i < NS + 3; i++) {
            if (i + PD < NS) ldsm_x4_t(a[(i + PD) % (PD + 1)], seq[i + PD] < 32 ? lc.a4 + (seq[i + PD] - 2) * 128 : lc.a8 + (seq[i + PD] - 34) * 256);
            if (i < 0) continue;
#pragma unroll
            for (int T = T0; T < T1; T++) {
                if (i >= NS) break;
                const int ee = seq[i] < 32 ? 2 * T - 6 - seq[i] : T + 35 - seq[i];
                if (i == 0 && T >= TC) mma_bf16(acc[T - T0], P, 0u, S, P, bq[2 * (T - TC)], bq[2 * (T - TC) + 1]);
                if (i == 1 && T >= TC) mma_bf16_k8(acc[T - T0], 0u, S, bq[20 + T - TC]);
                if (i == (T >= TC ? 2 : 0)) mma_bf16(acc[T - T0], f[19].x, 0u, f[19].y, f[19].x, bq[2 * (T - TC + 4)], bq[2 * (T - TC + 4) + 1]);
                if (seq[i] < 32 ? ee >= 0 && ee <= 9 : ee >= 10) mma_bf16(acc[T - T0], a[i % (PD + 1)][0], a[i % (PD + 1)][1], a[i % (PD + 1)][2], a[i % (PD + 1)][3], f[ee].x, f[ee].y);
            }
#pragma unroll
            for (int k = 0; k < 3; k++) {
                const int o = 256 * T0 + 512 * k;
                auto at = [&](int d) { return i - d >= 0 && i - d < NS && seq[i - d < 0 ? 0 : i - d < NS ? i - d : 0] == 2 * T0 + 4 * k - 4; };
                if (at(CV_D2)) {
                    cv_store(dq + lc.go + o, xv, yv);
                    if (layer > 19 - 2 * k) __trap();
                }
                if (at(-2)) { ldsm_x4_t(yw, lc.y + o); ldsm_x4_t(yz, lc.y + 3584 + o); }
                if (at(1)) {
#pragma unroll
                    for (int q = 0; q < 4; q++) yw[q] = add2(add2(yw[q], yz[q]), pack2(acc[2 * k + (q >> 1)][2 * (q & 1)], acc[2 * k + (q >> 1)][2 * (q & 1) + 1]));
                    stsm_x4_t(lc.y + o, yw[0], yw[1], yw[2], yw[3]);
                    xv = lds4(smem_u32(Xs + c * XLEN) + o + lane * 16);
                    __syncwarp();
                    yv = lds4(smem_u32(sm + CV_SM_Y) + c * 8192 + o + usw(lane) * 16);
                    if (layer > 20 - 2 * k) __trap();
                    if (k == 2) CST(6);
                }
            }
        }
    };
    TSTAMP1X(9, 256);
    if (threadIdx.x >= 256) {
        CV_IDX
        const int t2 = tid - 256, wgu = (warp >> 2) & 1, g = lane >> 2, ti = lane & 3;
        if (t2 == 0) {
            mbar_init(cnt + 48, 1);
            asm volatile("fence.mbarrier_init.release.cluster;" ::: "memory");
            mbar_expect_tx(cnt + 48, CV_CPB * 2048);
            bulk_load(smem_u32(sm + CV_SM_O), tap + d0 * 128, CV_CPB * 2048, cnt + 48);
        } else if (lane == 0) {
            if (warp < 15) mbar_init(cnt + 8 * (warp - 9), warp == 14 ? 8 : 4);
            else if (layer) prefetch_tmap(&tmOut);
        }
        if (t2 < 140) {
            const int k = t2;
            const int off = k < 20 ? CV_SM_B + BX_5 + 8 * k : k < 40 ? CV_SM_B + BX_3 + 8 * (k - 20) : k < 74 ? CV_SM_B + BX_9 + 8 * (k - 40) : k < 108 ? CV_SM_B + BX_7 + 8 * (k - 74) : CV_SM_U + 8 * (k - 108);
            const int str = k < 108 ? BX_LEN : ULEN * 2;
#pragma unroll
            for (int c = 0; c < CV_CPB; c++) *reinterpret_cast<uint2*>(sm + off + c * str) = make_uint2(0, 0);
        }
        fence_async_smem();
        asm volatile("bar.arrive 3, 512;" ::: "memory");
        asm volatile("bar.sync 1, 256;" ::: "memory");
        TSTAMP1X(10, 256);
        asm volatile("setmaxnreg.inc.sync.aligned.u32 168;");
        const int hc = wgu ? warp & 3 : 4;
        const Lc lc = lane_consts(lane, hc);
        const uint32_t* E2[3];
#pragma unroll
        for (int k = 0; k < 3; k++) {
            const int i = min(t2 + 256 * k, 759), h = i / 76;
            E2[k] = reinterpret_cast<const uint32_t*>(sm + CV_SM_O) + 3 + i + (h >> 1) * 360 + (h & 1) * 52;
        }
        mbar_wait(cnt + 48, 0);
        TSTAMP1X(11, 256);
        {
            uint32_t w[3][4];
#pragma unroll
            for (int k = 0; k < 3; k++) { w[k][0] = E2[k][0]; w[k][1] = E2[k][1]; w[k][2] = E2[k][64]; w[k][3] = E2[k][65]; }
#pragma unroll
            for (int k = 0; k < 3; k++)
                *reinterpret_cast<uint4*>(sm + CV_SM_T + min(t2 + 256 * k, 759) * 16) =
                    make_uint4(__byte_perm(w[k][1], w[k][0], 0x7610), __byte_perm(w[k][3], w[k][2], 0x7610), __byte_perm(w[k][1], 0, 0x1032), __byte_perm(w[k][3], 0, 0x1032));
        }
        asm volatile("bar.sync 1, 256;" ::: "memory");
        const uint2* Tc = reinterpret_cast<const uint2*>(sm + CV_SM_T) + 16 + 76 * (warp & 2) + 8 * (warp & 1) + g - 2 * ti;
        uint2 fa[8][2], fn[8][2];
        auto near_taps = [&](uint2 (&f)[8][2], int c) {
#pragma unroll
            for (int m = 0; m < 8; m++) { f[m][0] = Tc[c * (TAPB / 8) + 16 * m]; f[m][1] = Tc[c * (TAPB / 8) + 16 * m - 8]; }
        };
        near_taps(fa, 3 * wgu);
        near_taps(fn, 2 - wgu);
        TSTAMP1X(12, 256); CST(0);
        uint32_t ya = smem_u32(sm + CV_SM_Y) + wgu * 8192 + (warp & 2) * 2048 + usw(2 * lane + (warp & 1)) * 16;
        uint64_t db = make_desc(smem_u32(Us + wgu * ULEN + UPADF), 16, 256, 3);
        if (wgu) asm volatile("bar.sync 6, 384;" ::: "memory");
        int c = wgu;
        auto chain = [&](const uint2 (&f)[8][2], auto&& meanwhile) {
            float acc[64];
            asm volatile("bar.sync %0, %1;" ::"r"(c ? 4 + wgu : 2), "r"(c ? 256 : 384) : "memory");
            TSTAMPC(1 + 3 * c);
            wgmma_fence();
#pragma unroll
            for (int m = 0; m < 8; m++) {
                wgmma_rs128(acc, f[m][0], f[m][1], db - (uint64_t)(2 * m), m);
                if (m == CV_HAND && c < 4) asm volatile("bar.arrive %0, 256;" ::"r"(5 - wgu) : "memory");
            }
            wgmma_commit();
            asm volatile("griddepcontrol.launch_dependents;" ::: "memory");
            TSTAMPC(2 + 3 * c); CST(13 + (c >> 1));
            meanwhile();
            wgmma_wait<0>();
            TSTAMPC(3 + 3 * c); CST(10 + (c >> 1));
            uint32_t w[16];
#pragma unroll
            for (int j = 0; j < 16; j++) w[j] = j ? pack2(acc[4 * j] + acc[4 * j - 2], acc[4 * j + 1] + acc[4 * j - 1]) : pack2(acc[0], acc[1]);
#pragma unroll
            for (int j = 0; j < 16; j += 4) stsm_x4_t(ya + 256 * j, w[j], w[j + 1], w[j + 2], w[j + 3]);
            __syncwarp();
            if (lane == 0) mbar_arrive(cnt + 8 * c);
            c += 2; ya += 16384; db += ULEN / 4;
        };
        const uint32_t e4 = lc.e4, e8 = e4 + 428 - 4 * g;
        uint2 fl[4];
        uint32_t kk;
#pragma unroll 1
        for (;;) {
            if (c != 1) chain(fa, [&] {
                if (c == 3 || warp + c == 12) {
#pragma unroll
                    for (int k = 0; k < 19; k++) (k < 16 ? fn[(k >> 1) & 7][k & 1] : fl[k & 3]) = make_uint2(lds1(k < 10 ? e4 + 32 * k + 16 : e8 + 32 * k - 304), lds1(k < 10 ? e4 + 32 * k : e8 + 32 * k - 320));
                    fl[3] = make_uint2(lds1(lc.en), lds1(lc.en - 64));
                    kk = lds1(smem_u32(sm + CV_SM_O) + 2048 * hc + 1672);
                }
            });
            if (c > 4) break;
            if (c == 2) asm volatile("bar.sync 7, 384;" ::: "memory");
            chain(fn, [&] { if (c == 2) near_taps(fa, 4); });
        }
        TSTAMP1X(6, 256); CST(2);
        if (wgu || warp == 8) {
            constexpr int seq[29] = {5, 6, 32, 7, 33, 8, 34, 9, 35, 10, 36, 11, 12, 13, 14, 15, 16, 17, 37, 18, 38, 19, 20, 21, 39, 22, 40, 23, 24};
            uint2 f[20];
#pragma unroll
            for (int k = 0; k < 20; k++) f[k] = k < 16 ? fn[(k >> 1) & 7][k & 1] : fl[k & 3];
            far(Int<10>(), seq, lc, hc, lane, f, kk);
        }
    } else {
        asm volatile("setmaxnreg.dec.sync.aligned.u32 88;");
        CV_IDX
        const uint4* ppv = piv + tid;
        const float4* psv = sum + tid;
        const uint2* pxv = reinterpret_cast<const uint2*>(x1T + (size_t)d0 * XCP) + (tid >> 4) * 32 + (tid & 15);
        asm volatile("st.shared.u64 [%0], %1;" ::"r"(smem_u32(Xs) + tid * 16), "l"((uint64_t)ppv ^ (uint64_t)psv ^ (uint64_t)pxv) : "memory");
        const int tc = (0x04302100 >> (4 * warp)) & 7;
        const Lc lc = lane_consts(lane, tc);
        pdl_sync();
        SPAN(3 + 4 * layer, 1);
        TSTAMP(0); CST(0);
        if (tid == 0) TSTAMPC(0);
        if (threadIdx.x == 0) { GSTAMP(g_tim, 15); }
        float4 sv[4];
#pragma unroll
        for (int k = 0; k < 4; k++)
            asm volatile("ld.relaxed.gpu.global.v4.f32 {%0,%1,%2,%3}, [%4];" : "=f"(sv[k].x), "=f"(sv[k].y), "=f"(sv[k].z), "=f"(sv[k].w) : "l"(psv + 256 * k) : "memory");
        uint4 pv;
        asm volatile("ld.relaxed.gpu.global.v4.u32 {%0,%1,%2,%3}, [%4];" : "=r"(pv.x), "=r"(pv.y), "=r"(pv.z), "=r"(pv.w) : "l"(ppv) : "memory");
        uint2 xe[CV_CPB], xo[CV_CPB];
#pragma unroll
        for (int c = 0; c < CV_CPB; c++) {
            asm volatile("ld.relaxed.gpu.global.v2.u32 {%0,%1}, [%2];" : "=r"(xe[c].x), "=r"(xe[c].y) : "l"(pxv + c * (XCP / 4)) : "memory");
            asm volatile("ld.relaxed.gpu.global.v2.u32 {%0,%1}, [%2];" : "=r"(xo[c].x), "=r"(xo[c].y) : "l"(pxv + c * (XCP / 4) + 16) : "memory");
        }
        constexpr float idm = 1.0f / DM;
        uint32_t mw[4];
        float rs[8];
#pragma unroll
        for (int k = 0; k < 4; k++) {
            const uint32_t pw = k == 0 ? pv.x : k == 1 ? pv.y : k == 2 ? pv.z : pv.w;
            const float d0_ = sv[k].x * idm, d1_ = sv[k].z * idm;
            mw[k] = pack2(__uint_as_float(pw << 16) + d0_, __uint_as_float(pw & 0xffff0000u) + d1_);
            const uint32_t vr = pack2(fmaxf(fmaf(-d0_, d0_, sv[k].y * idm), 0.f), fmaxf(fmaf(-d1_, d1_, sv[k].w * idm), 0.f));
            const uint32_t ve = pack2(__uint_as_float(vr << 16) + 1e-5f, __uint_as_float(vr & 0xffff0000u) + 1e-5f);
            const uint32_t sd = pack2(sqrt_apx(__uint_as_float(ve << 16)), sqrt_apx(__uint_as_float(ve & 0xffff0000u)));
            rs[2 * k] = rcp_apx(__uint_as_float(sd << 16)); rs[2 * k + 1] = rcp_apx(__uint_as_float(sd & 0xffff0000u));
        }
        if (rs[0] != 123.f) TSTAMP(13);
        const uint32_t ua = smem_u32(Us) + usw(tid + UPADF / 8) * 16;
        uint32_t uw[CV_CPB][4];
#pragma unroll
        for (int c = 0; c < CV_CPB; c++) {
            const uint32_t e0 = sub2(xe[c].x, mw[0]), e1 = sub2(xe[c].y, mw[1]), o0 = sub2(xo[c].x, mw[2]), o1 = sub2(xo[c].y, mw[3]);
            uw[c][0] = pack2(__uint_as_float(e0 << 16) * rs[0], __uint_as_float(o0 << 16) * rs[4]); uw[c][1] = pack2(__uint_as_float(e0 & 0xffff0000u) * rs[1], __uint_as_float(o0 & 0xffff0000u) * rs[5]);
            uw[c][2] = pack2(__uint_as_float(e1 << 16) * rs[2], __uint_as_float(o1 << 16) * rs[6]); uw[c][3] = pack2(__uint_as_float(e1 & 0xffff0000u) * rs[3], __uint_as_float(o1 & 0xffff0000u) * rs[7]);
            asm volatile("st.shared.v4.u32 [%0], {%1,%2,%3,%4};" ::"r"(ua + c * ULEN * 2), "r"(uw[c][0]), "r"(uw[c][1]), "r"(uw[c][2]), "r"(uw[c][3]) : "memory");
            if (c < 2) {
                fence_async_smem();
                asm volatile("bar.arrive %0, 384;" ::"r"(2 + 4 * c) : "memory");
                if (layer > 29 - c) __trap();
            }
        }
        fence_async_smem();
#pragma unroll
        for (int c = 0; c < CV_CPB; c++) *reinterpret_cast<uint4*>(Xs + c * XLEN + tid * 8) = make_uint4(xe[c].x, xe[c].y, xo[c].x, xo[c].y);
        asm volatile("bar.arrive 7, 384;" ::: "memory");
        asm volatile("bar.sync 3, 512;" ::: "memory");
        TSTAMP(1); CST(1);
        {
            auto box = [&](auto c0, auto c1, int chunk, int cb, bool full) {
                const uint32_t ea = smem_u32(Us + cb * ULEN) + usw(chunk + UPADF / 8 + (lane ? 1 : -1)) * 16, bx = smem_u32(sm + CV_SM_B + cb * BX_LEN) + chunk * 16;
                uint32_t lo[CV_CPB][4], hi[CV_CPB][2];
#pragma unroll
                for (int c = c0; c < c1; c++) {
                    lo[c][0] = 0;
#pragma unroll
                    for (int k = 1; k < 4; k++) lo[c][k] = __shfl_up_sync(~0u, uw[c][k], 1);
#pragma unroll
                    for (int k = 0; k < 2; k++) hi[c][k] = __shfl_down_sync(~0u, uw[c][k], 1);
                }
#pragma unroll
                for (int c = c0; c < c1; c++)
                    asm volatile("{\n.reg .pred p, q;\nsetp.eq.s32 p, %7, 0;\nsetp.eq.s32 q, %7, 31;\n@p ld.shared.v4.u32 {%0,%1,%2,%3}, [%6];\n@q ld.shared.v2.u32 {%4,%5}, [%6];\n}"
                                 : "+r"(lo[c][0]), "+r"(lo[c][1]), "+r"(lo[c][2]), "+r"(lo[c][3]), "+r"(hi[c][0]), "+r"(hi[c][1]) : "r"(ea + c * ULEN * 2), "r"(lane) : "memory");
#pragma unroll
                for (int c = c0; c < c1; c++) {
                    const uint32_t e[9] = {lo[c][1], lo[c][2], lo[c][3], uw[c][0], uw[c][1], uw[c][2], uw[c][3], hi[c][0], hi[c][1]};
                    uint32_t o[8], p[8], t[7], b3[5], b5[7];
#pragma unroll
                    for (int i = 0; i < 8; i++) { o[i] = __byte_perm(e[i], e[i + 1], 0x5432); p[i] = add2(e[i], o[i]); }
#pragma unroll
                    for (int i = 0; i < 5; i++) b3[i] = add2(o[i], p[i + 1]);
                    sts4(bx + c * BX_LEN + BX_3 + 160, b3);
#pragma unroll
                    for (int i = 1; i < 7; i++) { t[i] = add2(p[i], p[i + 1]); b5[i] = add2(t[i], e[i + 2]); }
                    sts4(bx + c * BX_LEN + BX_5 + 160, b5 + 2);
                    if (full) {
#pragma unroll
                        for (int i = 1; i < 5; i++) { b3[i] = add2(b3[i], t[i + 2]); t[i] = add2(t[i], b5[i + 2]); }
                        sts4(bx + c * BX_LEN + BX_7 + 272, b3 + 1);
                        sts4(bx + c * BX_LEN + BX_9 + 272, t + 1);
                    }
                }
            };
            auto reload = [&](int c, uint32_t a) { const uint4 v = lds4(a); uw[c][0] = v.x; uw[c][1] = v.y; uw[c][2] = v.z; uw[c][3] = v.w; };
            if (warp >= 6) {
#pragma unroll
                for (int c = 0; c < 3; c++) reload(c, ua - 1024 + (c + 2) * ULEN * 2);
            }
            if (warp >= 4) {
#pragma unroll
                for (int c = 3; c < 5; c++) reload(c, ua - 2048 + c * ULEN * 2);
            }
            box(Int<0>(), Int<3>(), warp < 6 ? tid : tid - 64, warp < 6 ? 0 : 2, warp < 4);
            if (warp >= 4) box(Int<3>(), Int<5>(), tid - 128, 0, true);
            else if (tid >= 128 - CV_CPB) {
                const int c = 127 - tid;
                const uint2 v = *reinterpret_cast<const uint2*>(Us + c * ULEN + UPADF);
                const float s1 = __uint_as_float(v.x << 16), s2 = s1 + __uint_as_float(v.x & 0xffff0000u), s3 = s2 + __uint_as_float(v.y << 16), s4 = s3 + __uint_as_float(v.y & 0xffff0000u);
                unsigned char* bc = sm + CV_SM_B + c * BX_LEN;
                *reinterpret_cast<uint32_t*>(bc + BX_5 + 156) = pack2(s1, s2);
                *reinterpret_cast<uint2*>(bc + BX_7 + 264) = make_uint2(v.x << 16, pack2(s2, s3));
                *reinterpret_cast<uint2*>(bc + BX_9 + 264) = make_uint2(pack2(s1, s2), pack2(s3, s4));
            }
        }
        __syncwarp();
        if (lane == 0) mbar_arrive(cnt + 40);
        TSTAMP(2); CST(2);
        if (layer && blockIdx.x == 0 && tid == 224) g_epoch = ld_epoch();
        __syncwarp();
        if ((0x6e >> warp) & 1) {
            constexpr int seq[16] = {0, 1, 2, 3, 4, 5, 6, 32, 7, 8, 9, 33, 10, 34, 11, 12};
            uint2 f[20];
            mbar_wait(cnt, 0);
            const uint32_t e8 = lc.e4 + 428 - (lane & 28);
#pragma unroll
            for (int k = 0; k < 13; k++) f[k] = make_uint2(lds1(k < 10 ? lc.e4 + 32 * k + 16 : e8 + 32 * k - 304), lds1(k < 10 ? lc.e4 + 32 * k : e8 + 32 * k - 320));
            f[19] = make_uint2(lds1(lc.en), lds1(lc.en - 64));
            far(Int<4>(), seq, lc, tc, lane, f, lds1(smem_u32(sm + CV_SM_O) + 2048 * tc + 1672));
        }
    }
    {
        CV_IDX
        if ((0xc91 >> warp) & 1) {
            const int c = __popc(0xc91 & ((1 << warp) - 1));
            uint4 xv[2], yv[2];
#pragma unroll
            for (int k = 0; k < 2; k++) xv[k] = lds4(smem_u32(Xs + c * XLEN) + 512 * k + lane * 16);
            const uint32_t u0 = lds1(smem_u32(Us + c * ULEN) + (lane == 31 ? UPADF * 2 : 0));
            mbar_wait(cnt + 8 * c, 0);
#pragma unroll
            for (int k = 0; k < 2; k++) yv[k] = lds4(smem_u32(sm + CV_SM_Y) + c * 8192 + 512 * k + usw(lane) * 16);
            const uint4 yz = lds4(smem_u32(sm + CV_SM_Y) + c * 8192 + 4096 + usw(lane) * 16);
            const float kk = __uint_as_float(lds1(smem_u32(sm + CV_SM_O) + 2048 * c + 1272) << 16);
            yv[1].x = add2(yv[1].x, yz.x); yv[1].y = add2(yv[1].y, yz.y); yv[1].z = add2(yv[1].z, yz.z);
            yv[1].w = pack2(fmaf(kk, __uint_as_float(u0 << 16), __uint_as_float(yv[1].w << 16) + __uint_as_float(yz.w << 16)),
                            fmaf(kk, __uint_as_float(u0 << 16) + __uint_as_float(u0 & 0xffff0000u), __uint_as_float(yv[1].w & 0xffff0000u) + __uint_as_float(yz.w & 0xffff0000u)));
#pragma unroll
            for (int k = 0; k < 2; k++) cv_store(dq + c * XCP * 2 + (lane >> 4) * 256 + (lane & 15) * 8 + 512 * k, xv[k], yv[k]);
        }
        TSTAMP(4); CST(8);
        if (layer == 1) {
            const int rb = (blockIdx.x >> 3) + (warp & 8) * 2, cg = blockIdx.x & 7, ch = (tid >> 3) & 31;
            const bf16* src = dst + (size_t)(cg * 80 + ch) * XCP + rb * 64 + (tid & 7) * 8;
            uint32_t v[3][4];
            __syncthreads();
            if (warp & 8) { const uint32_t c0 = clock(); while (clock() - c0 < 300) ; }
            uint32_t todo = (warp & 4) ? 3 : 7;
#pragma unroll 1
            for (int it = 0; it < SPIN_MAX; it++) {
#pragma unroll
                for (int k = 0; k < 3; k++)
                    if (todo >> k & 1)
                        asm volatile("ld.relaxed.gpu.global.v4.u32 {%0,%1,%2,%3}, [%4];" : "=r"(v[k][0]), "=r"(v[k][1]), "=r"(v[k][2]), "=r"(v[k][3]) : "l"(src + k * (32 * XCP)) : "memory");
#pragma unroll
                for (int k = 0; k < 3; k++)
                    if ((todo >> k & 1) && v[k][0] != ~0u && v[k][1] != ~0u && v[k][2] != ~0u && v[k][3] != ~0u) {
                        *reinterpret_cast<uint4*>(sm + (32 * k + ch) * 272 + ((tid & 7) + (warp & 8)) * 16) = make_uint4(v[k][0], v[k][1], v[k][2], v[k][3]);
                        todo ^= 1u << k;
                    }
                if (!todo) break;
                __nanosleep(CV_SLEEP);
            }
            __syncwarp();
            asm volatile("bar.sync %0, 256;" ::"r"(8 + (warp >> 3)) : "memory");
            uint32_t w[12];
#pragma unroll
            for (int k = 0; k < 3; k++) ldsm_x4(&w[4 * k], smem_u32(sm) + min(32 * k + lane, 79) * 272 + warp * 16);
            const uint32_t ot = smem_u32(sm + CV_SM_O) + warp * 1280, oa = ot + (lane & 7) * 160 + (lane >> 3) * 16;
            stsm_x4_t(oa, w[0], w[1], w[2], w[3]);
            stsm_x4_t(oa + 64, w[4], w[5], w[6], w[7]);
            asm volatile("stmatrix.sync.aligned.m8n8.x2.trans.shared.b16 [%0], {%1,%2};" ::"r"(oa + 128), "r"(w[8]), "r"(w[9]) : "memory");
            fence_async_smem();
            __syncwarp();
            if (lane == 0) {
                asm volatile("cp.async.bulk.tensor.3d.global.shared::cta.bulk_group [%0, {%1, %2, %3}], [%4];" ::"l"(&tmOut), "r"(cg * 80), "r"((rb >> 1) * 64 + 8 * (warp & 7)), "r"(rb & 1), "r"(ot) : "memory");
                asm volatile("cp.async.bulk.commit_group;" ::: "memory");
                asm volatile("cp.async.bulk.wait_group.read 0;" ::: "memory");
            }
        }
    }
    TSTAMP(3); CST(9); CST_END;
    GSTAMP(g_tim, 14);
    SPAN(3 + 4 * layer, 3);
}

template <int TA, int TB>
__device__ __forceinline__ void wgmma_n240(float (&d)[120], uint64_t da, uint64_t db, int acc) {
    asm volatile("{\n.reg .pred p;\nsetp.ne.b32 p, %124, 0;\nwgmma.mma_async.sync.aligned.m64n240k16.f32.bf16.bf16 {%0,%1,%2,%3,%4,%5,%6,%7,%8,%9,%10,%11,%12,%13,%14,%15,%16,%17,%18,%19,%20,%21,%22,%23,%24,%25,%26,%27,%28,%29,%30,%31,%32,%33,%34,%35,%36,%37,%38,%39,%40,%41,%42,%43,%44,%45,%46,%47,%48,%49,%50,%51,%52,%53,%54,%55,%56,%57,%58,%59,%60,%61,%62,%63,%64,%65,%66,%67,%68,%69,%70,%71,%72,%73,%74,%75,%76,%77,%78,%79,%80,%81,%82,%83,%84,%85,%86,%87,%88,%89,%90,%91,%92,%93,%94,%95,%96,%97,%98,%99,%100,%101,%102,%103,%104,%105,%106,%107,%108,%109,%110,%111,%112,%113,%114,%115,%116,%117,%118,%119}, %120, %121, p, 1, 1, %122, %123;\n}"
                 : "+f"(d[0]), "+f"(d[1]), "+f"(d[2]), "+f"(d[3]), "+f"(d[4]), "+f"(d[5]), "+f"(d[6]), "+f"(d[7]), "+f"(d[8]), "+f"(d[9]), "+f"(d[10]), "+f"(d[11]), "+f"(d[12]), "+f"(d[13]), "+f"(d[14]), "+f"(d[15]), "+f"(d[16]), "+f"(d[17]), "+f"(d[18]), "+f"(d[19]), "+f"(d[20]), "+f"(d[21]), "+f"(d[22]), "+f"(d[23]), "+f"(d[24]), "+f"(d[25]), "+f"(d[26]), "+f"(d[27]), "+f"(d[28]), "+f"(d[29]), "+f"(d[30]), "+f"(d[31]), "+f"(d[32]), "+f"(d[33]), "+f"(d[34]), "+f"(d[35]), "+f"(d[36]), "+f"(d[37]), "+f"(d[38]), "+f"(d[39]), "+f"(d[40]), "+f"(d[41]), "+f"(d[42]), "+f"(d[43]), "+f"(d[44]), "+f"(d[45]), "+f"(d[46]), "+f"(d[47]), "+f"(d[48]), "+f"(d[49]), "+f"(d[50]), "+f"(d[51]), "+f"(d[52]), "+f"(d[53]), "+f"(d[54]), "+f"(d[55]), "+f"(d[56]), "+f"(d[57]), "+f"(d[58]), "+f"(d[59]), "+f"(d[60]), "+f"(d[61]), "+f"(d[62]), "+f"(d[63]), "+f"(d[64]), "+f"(d[65]), "+f"(d[66]), "+f"(d[67]), "+f"(d[68]), "+f"(d[69]), "+f"(d[70]), "+f"(d[71]), "+f"(d[72]), "+f"(d[73]), "+f"(d[74]), "+f"(d[75]), "+f"(d[76]), "+f"(d[77]), "+f"(d[78]), "+f"(d[79]), "+f"(d[80]), "+f"(d[81]), "+f"(d[82]), "+f"(d[83]), "+f"(d[84]), "+f"(d[85]), "+f"(d[86]), "+f"(d[87]), "+f"(d[88]), "+f"(d[89]), "+f"(d[90]), "+f"(d[91]), "+f"(d[92]), "+f"(d[93]), "+f"(d[94]), "+f"(d[95]), "+f"(d[96]), "+f"(d[97]), "+f"(d[98]), "+f"(d[99]), "+f"(d[100]), "+f"(d[101]), "+f"(d[102]), "+f"(d[103]), "+f"(d[104]), "+f"(d[105]), "+f"(d[106]), "+f"(d[107]), "+f"(d[108]), "+f"(d[109]), "+f"(d[110]), "+f"(d[111]), "+f"(d[112]), "+f"(d[113]), "+f"(d[114]), "+f"(d[115]), "+f"(d[116]), "+f"(d[117]), "+f"(d[118]), "+f"(d[119])
                 : "l"(da), "l"(db), "n"(TA), "n"(TB), "r"(acc));
}

__device__ __forceinline__ void wgmma_n80(float (&d)[40], uint64_t da, uint64_t db, int acc) {
    asm volatile("{\n.reg .pred p;\nsetp.ne.b32 p, %42, 0;\nwgmma.mma_async.sync.aligned.m64n80k16.f32.bf16.bf16 {%0,%1,%2,%3,%4,%5,%6,%7,%8,%9,%10,%11,%12,%13,%14,%15,%16,%17,%18,%19,%20,%21,%22,%23,%24,%25,%26,%27,%28,%29,%30,%31,%32,%33,%34,%35,%36,%37,%38,%39}, %40, %41, p, 1, 1, 0, 1;\n}"
                 : "+f"(d[0]), "+f"(d[1]), "+f"(d[2]), "+f"(d[3]), "+f"(d[4]), "+f"(d[5]), "+f"(d[6]), "+f"(d[7]), "+f"(d[8]), "+f"(d[9]), "+f"(d[10]), "+f"(d[11]), "+f"(d[12]), "+f"(d[13]), "+f"(d[14]), "+f"(d[15]), "+f"(d[16]), "+f"(d[17]), "+f"(d[18]), "+f"(d[19]), "+f"(d[20]), "+f"(d[21]), "+f"(d[22]), "+f"(d[23]), "+f"(d[24]), "+f"(d[25]), "+f"(d[26]), "+f"(d[27]), "+f"(d[28]), "+f"(d[29]), "+f"(d[30]), "+f"(d[31]), "+f"(d[32]), "+f"(d[33]), "+f"(d[34]), "+f"(d[35]), "+f"(d[36]), "+f"(d[37]), "+f"(d[38]), "+f"(d[39])
                 : "l"(da), "l"(db), "r"(acc));
}

constexpr int A1_THREADS = 384;
constexpr int A1_NST = 4;
#define A1_SKEW 8
constexpr int A1_STAGE = 16384 + WQ_STAGE;
constexpr int A1_KVP = 336;
constexpr int A1_SM_KV = 2 * A1_STAGE;
constexpr int A1_SM_BAR = A1_NST * A1_STAGE;
constexpr int A1_SM_RS = A1_SM_BAR + 512;
constexpr int A1_SM_W0 = A1_SM_BAR + 3072, A1_SM_W3 = A1_SM_BAR - 3 * WOB, A1_SM_A1 = 2 * WOB, A1_SM_A0 = A1_SM_A1 + 61440;
constexpr int A1_SM_XA = A1_SM_W0 + 2 * WOB, A1_SM_XB = A1_SM_XA + 2048;
constexpr int A1_SMEM = A1_SM_W0 + 3 * WOB + CST_EXTRA;
static_assert(A1_SM_W3 >= A1_SM_KV + 144 * A1_KVP && A1_SM_W3 % 512 == 0 && A1_SM_A1 % 1024 == 0 && A1_SM_A0 <= A1_SM_KV && A1_SM_A0 + 61440 <= A1_SM_W3 && A1_SMEM <= 232448, "layout");
__device__ __forceinline__ constexpr uint32_t wo_off(int h) { return h * WOB + (h < 3 ? A1_SM_W0 : h < 6 ? A1_SM_W3 - 3 * WOB : -6 * WOB); }
#define A1_FRED "red.relaxed.gpu.global.add.u32"
#define A1_FLD "ld.acquire.gpu.global.u32"
#define ST_SLEEP 20
#define ST_SLEEP0 300
#define WO_LATE bar_done
#define A1_P0 2
#define A1_PW (kb - 2)
#define A1_FSPIN SPIN_MAX
#define A1_FSLEEP 40
#define YT_LAYER 1
#define WOT 352
#define A1_WOAT 6

template <int L>
__device__ __forceinline__ void a1_mainloop(float (&acc)[120], uint32_t sbase, uint32_t bars, int wg, int tile) {
    constexpr int layer = L; (void)layer;
    const uint64_t da0 = L ? make_desc(sbase + wg * 8192, 8192, 1024, 1) : make_desc(sbase + wg * 8192, 16, 1024, 1), db0 = make_desc(sbase + 16384, 1024, 256, 3);
#pragma unroll 1
    for (int t = 0;; t++) {
        const int st = t % A1_NST;
        mbar_wait(bars + 8 * st, (t / A1_NST) & 1);
        if (t == A1_SKEW && wg == 0) mbar_wait(bars + 160, 0);
        TSTAMP3(1 + t);
        if (t == 0) CSA(0);
        wgmma_fence();
#pragma unroll
        for (int kk = 0; kk < 4; kk++) wgmma_n240<L, 1>(acc, da0 + (uint32_t)(st * (A1_STAGE / 16) + kk * (L ? 128 : 2)), db0 + (uint32_t)(st * (A1_STAGE / 16) + (kk >> 1) * (WQ_STAGE / 32) + (kk & 1) * 32), kk ? 1 : t);
        wgmma_commit();
        if (t == 9) break;
        if (t == A1_SKEW - 1 && wg == 0) wgmma_wait<0>(); else wgmma_wait<1>();
        if (t > 0 && (threadIdx.x & 127) == 0) {
            if (t != A1_SKEW || wg) mbar_arrive(bars + 8 * (A1_NST + (t - 1) % A1_NST));
            if (t == A1_SKEW - 1 && wg == 0) mbar_arrive(bars + 8 * (A1_NST + t % A1_NST));
        }
    }
}

__global__ void __launch_bounds__(A1_THREADS, 1) a1_kernel(const int layer, const bf16* __restrict__ x0, const unsigned char* __restrict__ wq, const unsigned char* __restrict__ wo,
                                                           float2* __restrict__ rsum, uint4* __restrict__ of, const __grid_constant__ CUtensorMap tmX,
                                                           const __grid_constant__ CUtensorMap tmR, const __grid_constant__ CUtensorMap tmX1, const __grid_constant__ TileTab tab) {
    extern __shared__ __align__(1024) unsigned char stg[];
    const uint32_t sbase = smem_u32(stg);
    const uint32_t bars = sbase + A1_SM_BAR;
    const uint32_t bar_stat = bars + 64, bar_kv = bars + 72, bar_rd = bars + 168;
    const uint32_t bar_wo = bars + 208, bar_done = bars + 216, bar_pv = bars + 224, bar_kvf = bars + 232, bar_f2 = bars + 248, bar_e2 = bars + 384, que = bars + 448;
    const int tid = threadIdx.x;
    const int w = __shfl_sync(~0u, tid >> 5, 0), wg = w >> 2;
    uint32_t smid, ns;
    asm volatile("mov.u32 %0, %smid;" : "=r"(smid));
    asm volatile("mov.u32 %0, %nsmid;" : "=r"(ns));
    const auto te = tab.e[ns == tab.ns ? smid : 132 + blockIdx.x];
    const int tile = te.tile, mb = te.mb, hg = te.hg;
    float2* rst = reinterpret_cast<float2*>(stg + A1_SM_RS) + 8;
    auto issue_w = [&](int it) { bulk_load(sbase + (it % A1_NST) * A1_STAGE + 16384, wq + te.woff + it * WQ_STAGE, WQ_STAGE, bars + 8 * (it % A1_NST)); };
    auto issue_x = [&](int it, int kb) {
        asm volatile("cp.async.bulk.tensor.5d.shared::cluster.global.mbarrier::complete_tx::bytes [%0], [%1, {%3, %3, %3, %4, %5}], [%2];"
                     ::"r"(sbase + (it % A1_NST) * A1_STAGE), "l"(&tmX), "r"(bars + 8 * (it % A1_NST)), "r"(0), "r"(mb), "r"(kb) : "memory");
    };
    if (w == 8 && tile < 128) {
        const bool one = elect();
        if (one) {
#pragma unroll
            for (int i = 0; i < A1_NST; i++) mbar_init(bars + 8 * i, 1);
            asm volatile("fence.mbarrier_init.release.cluster;" ::: "memory");
        }
        __syncwarp();
        asm volatile("bar.arrive 0, 384;" ::: "memory");
        if (one) {
#define PW asm volatile("griddepcontrol.wait;" ::: "memory");
            if (layer) { issue_w(0); PW issue_x(0, te.kb0); issue_x(1, te.kb0 + 1); }
            else { issue_x(0, te.kb0); issue_x(1, te.kb0 + 1); PW issue_w(0); }
            issue_w(1);
#pragma unroll
            for (int i = 0; i < A1_NST; i++) mbar_expect_tx(bars + 8 * i, A1_STAGE);
            asm volatile("griddepcontrol.launch_dependents;" ::: "memory");
#pragma unroll
            for (int kb = 2; kb < A1_P0; kb++) { issue_x(kb, te.kb0 + kb); issue_w(kb); }
            DBGC(34); DBGV(33, smid); DBGV(40, t_entry); DBGV(30, t_a); DBGV(31, t_b); DBGV(32, t_c); DBGV(38, t_d); DBGV(39, t_e);
        }
    }
    if (tile >= 128) { sm_idle(layer); return; }
    if (wg == 2) {
        if (w != 8) {
            if (tid == 320) { prefetch_tmap(&tmX); prefetch_tmap(&tmR); prefetch_tmap(&tmX1); }
            if (w == 11 && layer == 0 && elect()) {
                mbar_init(bars + 240, 1);
                asm volatile("fence.mbarrier_init.release.cluster;" ::: "memory");
                mbar_expect_tx(bars + 240, 20480);
                bulk_load(sbase + A1_SM_W0, x0 + (size_t)(mb * 128 + hg * 16) * DM, 20480, bars + 240);
            }
            __syncwarp();
            asm volatile("bar.sync 0, 384;" ::: "memory");
        }
        if (w == 9) {
            asm volatile("bar.arrive 3, 64;" ::: "memory");
            if (layer == 0) pdl_sync();
            float4 a[2] = {};
#pragma unroll
            for (int k = 0; k < 10; k++)
#pragma unroll
                for (int h = 0; h < 2; h++) {
                    const int c4 = min(tid - 288 + 32 * h, 59);
                    const float4 v = __ldcg(reinterpret_cast<const float4*>(g_csp + k * 1920 + hg * 80) + c4 + (c4 / 20) * 140);
                    a[h].x += v.x; a[h].y += v.y; a[h].z += v.z; a[h].w += v.w;
                }
#pragma unroll
            for (int h = 0; h < 2; h++)
#pragma unroll
                for (int k = 0; k < 4; k++) {
                    const float c = 0.5f * (k == 0 ? a[h].x : k == 1 ? a[h].y : k == 2 ? a[h].z : a[h].w), c1 = c - rbf(c), c2 = c1 - rbf(c1);
                    *reinterpret_cast<uint4*>(stg + A1_SM_XB + (4 * min(tid - 288 + 32 * h, 59) + k) * 16) = make_uint4(pack2(c, c1), pack2(c2, 0.f), 0u, 0u);
                }
            fence_async_smem();
            __syncwarp();
            if (tid == 288) mbar_arrive(bar_stat);
            CSA(1);
#pragma unroll 4
            for (int k = 0; k < 40; k++) asm volatile("st.global.v4.u32 [%0], {%1,%1,%1,%1};" ::"l"(of + (mb * 8 + hg) * 1280 + 32 * k + (tid - 288)), "r"(~0u) : "memory");
            CSA(2);
            asm volatile("fence.acq_rel.gpu;" ::: "memory");
            asm volatile("fence.proxy.async.global;" ::: "memory");
            __syncwarp();
            if (tid == 288) mbar_arrive(bar_done);
            CSA(3);
            if (layer == YT_LAYER) {
#pragma unroll 4
                for (int k = tid - 288; k < 5 * XCP / 8; k += 32) asm volatile("st.global.v4.u32 [%0], {%1,%1,%1,%1};" ::"l"(reinterpret_cast<uint4*>(g_yT) + tile * (5 * XCP / 8) + k), "r"(~0u) : "memory");
            }
            TSTAMP1T(9, 288);
        } else if (w == 8) {
            asm volatile("bar.sync 3, 64;" ::: "memory");
            if (elect()) {
#pragma unroll 1
                for (int kb = A1_P0; kb < 10; kb++) {
                    if (kb < A1_NST) mbar_wait(bars + 8 * A1_PW, 0);
                    else {
                        mbar_wait(bars + 8 * (A1_NST + kb % A1_NST), ((kb / A1_NST) - 1) & 1);
                        if (layer && kb < 9) mbar_wait(bar_rd + 8 * (kb - A1_NST), 0);
                        mbar_expect_tx(bars + 8 * (kb % A1_NST), A1_STAGE);
                    }
                    issue_x(kb, kb < 5 ? kb + te.kb0 : kb - te.kb0); issue_w(kb);
                    if (kb == (layer ? A1_WOAT : 9)) {
                        if (!layer) mbar_wait(bar_rd + 32, 0);
                        mbar_expect_tx(bar_wo, 8 * WOB);
                        bulk_load(sbase + A1_SM_W0, wo + hg * 8 * WOB, 2 * WOB, bar_wo);
                    }
                }
                TSTAMP1T(6, 256);
                mbar_wait(bars + 8 * (A1_NST + 3), 1);
                bulk_load(sbase + A1_SM_W3, wo + (hg * 8 + 3) * WOB, 3 * WOB, bar_wo);
            }
            __syncwarp();
        } else {
            const int j = tid - 320;
            const uint32_t tag = ld_epoch();
            if (tid == 352) sm_started(layer);
            const int ch = j & 7, kg = (j >> 3) & 3;
            const unsigned char* src = stg + (layer ? (j >> 5) * 8192 + (hg & 3) * 2048 : A1_SM_W0 + (j >> 2) * 1280);
            const int of0 = layer ? kg * 128 + ((ch ^ kg) << 4) : (j & 7) << 4, ofx = layer ? 576 : 64, ofy = layer ? 1024 : 128;
            float s[8], q[8], p0[8];
#pragma unroll
            for (int i = 0; i < 8; i++) { s[i] = 0.f; q[i] = 0.f; }
#pragma unroll 1
            for (int it = 0; it < 5; it++) {
                uint4 v[4];
                mbar_wait(layer ? bars + 8 * (it % A1_NST) : bars + 240, layer * it / A1_NST);
#pragma unroll
                for (int k = 0; k < 4; k++) v[k] = *reinterpret_cast<const uint4*>(src + (layer ? (it % A1_NST) * A1_STAGE : it * 256) + (k & 1 ? of0 ^ ofx : of0) + (k >> 1) * ofy);
                if (it == 0) {
                    const uint4 pv = *reinterpret_cast<const uint4*>(src + (layer ? ch << 4 : 0));
                    const uint32_t w[4] = {pv.x, pv.y, pv.z, pv.w};
#pragma unroll
                    for (int i = 0; i < 4; i++) { p0[2 * i] = __uint_as_float((layer ? w[i] : w[0]) << 16); p0[2 * i + 1] = __uint_as_float(layer ? w[i] & 0xffff0000u : w[0] << 16); }
                }
                asm volatile("" :: "r"(v[0].x), "r"(v[1].x), "r"(v[2].x), "r"(v[3].x), "f"(p0[0]) : "memory");
                __syncwarp();
                if ((tid & 31) == 0) mbar_arrive(bar_rd + 8 * it);
#pragma unroll
                for (int k = 0; k < 4; k++) {
                    const uint32_t w[4] = {v[k].x, v[k].y, v[k].z, v[k].w};
#pragma unroll
                    for (int i = 0; i < 4; i++) {
                        const float a = __uint_as_float(w[i] << 16) - p0[2 * i], b = __uint_as_float(w[i] & 0xffff0000u) - p0[2 * i + 1];
                        s[2 * i] += a; s[2 * i + 1] += b; q[2 * i] = fmaf(a, a, q[2 * i]); q[2 * i + 1] = fmaf(b, b, q[2 * i + 1]);
                    }
                }
            }
            float o[4];
            int row;
            if (layer == 0) {
                float s0 = ((s[0] + s[1]) + (s[2] + s[3])) + ((s[4] + s[5]) + (s[6] + s[7])), q0 = ((q[0] + q[1]) + (q[2] + q[3])) + ((q[4] + q[5]) + (q[6] + q[7]));
#pragma unroll
                for (int o = 1; o <= 2; o <<= 1) { s0 += __shfl_xor_sync(~0u, s0, o); q0 += __shfl_xor_sync(~0u, q0, o); }
                if ((j & 3) == 0) {
                    const float d = s0 * (1.0f / DM);
                    const uint32_t ms = pack2(p0[0] + d, sqrt_apx(rbf(rbf(fmaxf(fmaf(-d, d, q0 * (1.0f / DM)), 0.f)) + 1e-5f)));
                    asm volatile("st.global.cg.u64 [%0], %1;" ::"l"(g_rstat + mb * 128 + (j & 4) * 16 + hg * 8 + (j >> 3)), "l"(tagw(ms, tag)) : "memory");
                    g_piv[mb * 128 + hg * 16 + ((j >> 2) & 8) + (j & 4) + ((j >> 3) & 3)] = __ushort_as_bfloat16((unsigned short)ms);
                }
                ulonglong2 v;
#pragma unroll 1
                for (int it = 0; it < SPIN_MAX; it++) {
                    v = ld_tag2(reinterpret_cast<const ulonglong2*>(g_rstat + mb * 128) + j);
                    if (tag_ok(v, tag)) break;
                    __nanosleep(100);
                }
                o[0] = __uint_as_float((uint32_t)v.x << 16); o[1] = rcp_apx(__uint_as_float((uint32_t)v.x & 0xffff0000u));
                o[2] = __uint_as_float((uint32_t)v.y << 16); o[3] = rcp_apx(__uint_as_float((uint32_t)v.y & 0xffff0000u));
                row = 2 * j;
            } else {
#pragma unroll
                for (int i = 0; i < 4; i++) {
                    const bool up = kg & 2;
                    const float ss = __shfl_xor_sync(~0u, up ? s[i] : s[i + 4], 16), qq = __shfl_xor_sync(~0u, up ? q[i] : q[i + 4], 16);
                    s[i] = (up ? s[i + 4] : s[i]) + ss; q[i] = (up ? q[i + 4] : q[i]) + qq; p0[i] = up ? p0[i + 4] : p0[i];
                }
#pragma unroll
                for (int i = 0; i < 2; i++) {
                    const bool up = kg & 1;
                    const float ss = __shfl_xor_sync(~0u, up ? s[i] : s[i + 2], 8), qq = __shfl_xor_sync(~0u, up ? q[i] : q[i + 2], 8);
                    s[i] = (up ? s[i + 2] : s[i]) + ss; q[i] = (up ? q[i + 2] : q[i]) + qq; p0[i] = up ? p0[i + 2] : p0[i];
                }
                uint4* gp = g_halo + 86016 + mb * 512 + j;
                const float d0 = s[0] * (1.0f / 80.0f), d1 = s[1] * (1.0f / 80.0f);
                asm volatile("st.relaxed.gpu.global.v4.f32 [%0], {%1,%2,%3,%4};" ::"l"(gp + hg * 64), "f"(p0[0] + d0), "f"(fmaxf(fmaf(-d0, s[0], q[0]), 0.f)), "f"(p0[1] + d1), "f"(fmaxf(fmaf(-d1, s[1], q[1]), 0.f)) : "memory");
                __nanosleep(ST_SLEEP0);
                uint32_t pw[8][4], todo = 0xff;
#pragma unroll 1
                for (int it = 0; it < SPIN_MAX; it++) {
#pragma unroll
                    for (int k = 0; k < 8; k++)
                        if (todo >> k & 1) asm volatile("ld.relaxed.gpu.global.v4.u32 {%0,%1,%2,%3}, [%4];" : "=r"(pw[k][0]), "=r"(pw[k][1]), "=r"(pw[k][2]), "=r"(pw[k][3]) : "l"(gp + k * 64) : "memory");
#pragma unroll
                    for (int k = 0; k < 8; k++)
                        if (__all_sync(~0u, pw[k][0] != ~0u && pw[k][1] != ~0u && pw[k][2] != ~0u && pw[k][3] != ~0u)) todo &= ~(1u << k);
                    if (!todo) break;
                    __nanosleep(ST_SLEEP);
                }
#pragma unroll
                for (int r = 0; r < 2; r++) {
                    float mean = 0.f, m2 = 0.f;
#pragma unroll
                    for (int k = 0; k < 8; k++) mean += __uint_as_float(pw[k][2 * r]);
                    mean *= 0.125f;
#pragma unroll
                    for (int k = 0; k < 8; k++) {
                        const float dm = __uint_as_float(pw[k][2 * r]) - mean;
                        m2 += fmaf(80.0f * dm, dm, __uint_as_float(pw[k][2 * r + 1]));
                    }
                    o[2 * r] = rbf(mean);
                    o[2 * r + 1] = rcp_apx(rbf(sqrt_apx(rbf(rbf(m2 * (1.0f / DM)) + 1e-5f))));
                }
                row = (j >> 5) * 64 + (j & 7) * 8 + ((j >> 3) & 3) * 2;
                if (hg == 0) *reinterpret_cast<uint32_t*>(g_piv + SEQ + mb * 128 + 2 * (row & 60) + 4 * (row >> 6) + (row & 3)) = __byte_perm(__float_as_uint(o[0]), __float_as_uint(o[2]), 0x7632);
            }
#pragma unroll
            for (int r = 0; r < 2; r++)
                *reinterpret_cast<uint4*>(stg + A1_SM_XA + (row + r) * 16) = make_uint4(__byte_perm(__float_as_uint(-o[2 * r]), 0, 0x3232), __float_as_uint(-o[2 * r]) >> 16, 0u, 0u);
            *reinterpret_cast<float4*>(rst + row + (row >> 6) * 8) = make_float4(o[0], o[1], o[2], o[3]);
            fence_async_smem();
            TSTAMP1T(7, 320); CSA(1);
            if (tid == 320) DBGC(44);
            __syncwarp();
            if ((tid & 31) == 0) mbar_arrive(bar_stat);
        }
        CSA(4); CSA_END;
        if (tid == 320) DBGCAL(0);
        if (tid == WOT) {
            mbar_wait(WO_LATE, 0);
            mbar_wait(bar_done, 0);
            bulk_load(sbase, wo + (hg * 8 + 6) * WOB, 2 * WOB, bar_wo);
            bulk_load(sbase + A1_SM_W0 + 2 * WOB, wo + (hg * 8 + 2) * WOB, WOB, bar_wo);
        }
        __syncwarp();
#define FWA 11
#define FWB 10
        if (w == FWA || w == FWB) {
            const int cw = w == FWB;
            const uint32_t* fl = reinterpret_cast<const uint32_t*>(rsum + 2 * SEQ) + (((layer * 16 + mb) * 2 + cw) * 8 + (tid & 7)) * FSTR;
            const unsigned char* src = reinterpret_cast<const unsigned char*>(of) + mb * 163840 + cw * 10240 + (tid & 7) * 20480;
            const uint32_t sl = sbase + (cw ? A1_SM_A1 : A1_SM_A0);
            mbar_wait(cw ? bar_done : bar_kvf, 0);
            if ((tid & 31) == 0) {
                mbar_expect_tx(bar_f2 + 64 * cw + 64, 10240);
                tma_load_3d(sl + 51200, &tmR, layer ? 0 : hg * 80, layer ? hg * 80 : mb * 64, layer ? mb * 2 + cw : cw, bar_f2 + 64 * cw + 64);
            }
            __syncwarp();
            uint32_t pend = 0xffu & ~(1u << hg), v = 0;
            const uint32_t bo = wo_off((tid & 7) + ((tid & 7) < hg)) >> 4, lt = (1u << (tid & 31)) - 1;
#pragma unroll 1
            for (int it = 0; pend && it < 2 * SPIN_MAX; it++) {
                if (v != 4 && (pend >> (tid & 31) & 1)) asm volatile(A1_FLD " %0, [%1];" : "=r"(v) : "l"(fl) : "memory");
                uint32_t fr;
                asm volatile("{\n.reg .pred p;\nmbarrier.test_wait.parity.shared::cta.b64 p, [%1], 0;\nselp.b32 %0, 1, 0, p;\n}" : "=r"(fr) : "r"(bar_e2 + 16 * cw + (tid & 1) * 8) : "memory");
                fr = __ballot_sync(~0u, fr);
                uint32_t m = __ballot_sync(~0u, v == 4 || it >= A1_FSPIN) & pend;
                const int q = 8 - __popc(pend) + __popc(m & lt);
                m &= __ballot_sync(~0u, q < ((fr & 2) ? 8 : (fr & 1) ? 7 : 5));
                pend ^= m;
                if (m >> (tid & 31) & 1) DBGC(12 + cw * 8 + (tid & 7));
                if (!m) __nanosleep(A1_FSLEEP);
                else asm volatile("fence.proxy.async.global;" ::: "memory");
                if (m >> (tid & 31) & 1) {
                    bulk_load(q == 7 && !cw ? sbase + A1_SM_W0 : sl + (q < 6 ? q : q - 6) * 10240, src, 10240, bar_f2 + 64 * cw + 8 * q);
                    asm volatile("st.shared.u32 [%0], %1;" ::"r"(que + 32 * cw + 4 * q), "r"(bo) : "memory");
                    mbar_expect_tx(bar_f2 + 64 * cw + 8 * q, 10240);
                    DBGC(44 + cw * 8 + q);
                }
                __syncwarp();
            }
        }
    } else {
        if (tid == 0) {
            mbar_init(bar_stat, 3);
#pragma unroll
            for (int i = 0; i < 8; i++) mbar_init(bar_kv + 8 * i, 1);
            mbar_init(bars + 144, 1);
            mbar_init(bars + 160, 1);
#pragma unroll
            for (int i = 0; i < 5; i++) mbar_init(bar_rd + 8 * i, 2);
            asm volatile("fence.mbarrier_init.release.cluster;" ::: "memory");
        } else if (tid == 32) {
            mbar_init(bar_wo, 1); mbar_init(bar_done, 3); mbar_init(bar_pv, 4); mbar_init(bar_kvf, 8);
#pragma unroll
            for (int i = 0; i < 4; i++) { mbar_init(bar_e2 + 8 * i, i == 1 ? 2 : 1); mbar_init(bars + 8 * (A1_NST + i), 2); }
            asm volatile("fence.mbarrier_init.release.cluster;" ::: "memory");
        } else if (tid == 96) {
#pragma unroll
            for (int i = 0; i < 4; i++) mbar_init(bars + 416 + 8 * i, 1);
            asm volatile("fence.mbarrier_init.release.cluster;" ::: "memory");
        } else if (tid == 64) {
#pragma unroll
            for (int i = 1; i <= 16; i++) mbar_init(bar_f2 + 8 * i, 1);
            asm volatile("fence.mbarrier_init.release.cluster;" ::: "memory");
        }
        asm volatile("bar.sync 0, 384;" ::: "memory");
        SPAN(1 + 4 * layer, 0);
        constexpr int on = 1;
        float acc[120];
        const int lane = tid & 31, warp = w & 7, g = lane >> 2, t = lane & 3;
        if (on) {
            SPAN(1 + 4 * layer, 1);
            TSTAMP1(0);
            if (threadIdx.x == 0) { GSTAMP(g_tim1, 15); }
            TSTAMP3(0);
            if (tid == 0) TSTAMP2(0);
            TSTAMP4(0);
            if (tid == 0) DBGC(60);
            if (layer == 0) a1_mainloop<0>(acc, sbase, bars, wg, tile); else a1_mainloop<1>(acc, sbase, bars, wg, tile);
            uint32_t ok;
            asm volatile("{\n.reg .pred p;\nmbarrier.test_wait.parity.shared::cta.b64 p, [%1], 0;\nselp.b32 %0, 1, 0, p;\n}" : "=r"(ok) : "r"(bar_stat) : "memory");
            if (tid == 128 && !ok) mbar_arrive(bars + 160);
            __syncwarp();
            mbar_wait(bar_stat, 0);
            wgmma_fence();
            wgmma_n240<0, 0>(acc, make_desc(sbase + A1_SM_XA + wg * 1024, 0, 128, 0), make_desc(sbase + A1_SM_XB, 0, 128, 0), 1);
            wgmma_commit();
            if (tid == 128 && ok) mbar_arrive(bars + 160);
            mbar_wait(bars + 8 * (A1_NST + 3), 1);
        }
        const float2* rw = rst + 16 * warp + 8 * wg;
        const float rb0 = rw[g + 8].y, ra = rw[g].y * 0.22360679774997896f, rb = rb0 * 0.22360679774997896f;
        wgmma_wait<0>();
        if ((tid & 127) == 0) mbar_arrive(bar_done);
        TSTAMP1(2); CSA(1);
        TSTAMP1T(13, 224);
        if ((tid & 127) == 0) DBGC(62 - wg);
        uint32_t f[2][30];
#pragma unroll
        for (int j = 10; j < 30; j++) f[1][j] = pack2(acc[4 * j + 2], acc[4 * j + 3]);
        if ((warp & 3) == 3) {
            uint4* hout = g_halo + (((layer * 16 + mb) * 8 + hg) * 2 + wg) * 168;
#pragma unroll
            for (int j = 0; j < 20; j += 4)
                asm volatile("st.relaxed.gpu.global.v4.u32 [%0], {%1,%2,%3,%4};" ::"l"(hout + 8 * j + lane), "r"(f[1][10 + j]), "r"(f[1][11 + j]), "r"(f[1][12 + j]), "r"(f[1][13 + j]) : "memory");
            if (t == 0) asm volatile("st.relaxed.gpu.global.f32 [%0], %1;" ::"l"(reinterpret_cast<float*>(hout + 160) + g), "f"(rb0) : "memory");
        }
        TSTAMP1T(12, 224);
        const uint32_t kvw = sbase + A1_SM_KV + (16 * warp + 8 * wg) * A1_KVP;
        const uint32_t mrow = kvw + (lane & 7) * A1_KVP + (lane >> 3) * 16;
#pragma unroll
        for (int j = 0; j < 20; j += 4) stsm_x4(mrow + 16 * A1_KVP + 16 * j, f[1][10 + j], f[1][11 + j], f[1][12 + j], f[1][13 + j]);
        __syncwarp();
        if (lane == 0 && (warp & 3) != 3) mbar_arrive(bar_kv + 8 * (warp + 1));
#pragma unroll
        for (int j = 0; j < 30; j++) f[0][j] = pack2(acc[4 * j], acc[4 * j + 1]);
        stsm_x4(mrow + 8 * A1_KVP + 160, f[0][20], f[0][21], f[0][22], f[0][23]);
        stsm_x4(mrow + 8 * A1_KVP + 224, f[0][24], f[0][25], f[0][26], f[0][27]);
        asm volatile("stmatrix.sync.aligned.m8n8.x2.shared.b16 [%0], {%1,%2};" ::"r"(mrow + 8 * A1_KVP + 288), "r"(f[0][28]), "r"(f[0][29]) : "memory");
#pragma unroll
        for (int j = 0; j < 10; j++) f[1][j] = pack2(acc[4 * j + 2], acc[4 * j + 3]);
        __syncwarp();
        uint32_t vb[10][2], vp[12], kp[12];
#pragma unroll
        for (int j = 0; j < 10; j += 2) ldsm_x4_t(&vb[j][0], kvw + (8 + (lane & 15)) * A1_KVP + 160 + (lane >> 4) * 16 + 16 * j);
        const bool up0 = 2 * t > g, up1 = 2 * t + 1 > g, edge = (mb | (warp & 3)) == 0;
        float rk[4];
        auto above = [&]() {
            mbar_wait(bar_kv + 8 * warp, 0);
#pragma unroll
            for (int j = 0; j < 12; j += 4) ldsm_x4(&kp[j], mrow + 16 * j);
            rk[0] = rw[2 * t - (up0 ? 8 : 0)].y; rk[1] = rw[2 * t + 1 - (up1 ? 8 : 0)].y;
#pragma unroll
            for (int j = 0; j < 12; j += 4) ldsm_x4_t(&vp[j], mrow + 160 + 16 * j - (j == 8 ? (lane & 16) * 2 : 0));
            __syncwarp();
            if (lane == 0) mbar_arrive(bar_kvf);
        };
        auto halo = [&]() {
            if (lane == 0) mbar_arrive(bar_kvf);
            const uint4* hin = g_halo + (((layer * 16 + mb - 1) * 8 + hg) * 2 + wg) * 168;
            uint32_t hv[22] = {};
            rk[0] = rw[2 * t].y; rk[1] = rw[2 * t + 1].y;
            if (mb > 0) {
#pragma unroll 1
                for (int it = 0; it < SPIN_MAX; it++) {
#pragma unroll
                    for (int k = 0; k < 20; k += 4)
                        asm volatile("ld.relaxed.gpu.global.v4.u32 {%0,%1,%2,%3}, [%4];" : "=r"(hv[k]), "=r"(hv[k + 1]), "=r"(hv[k + 2]), "=r"(hv[k + 3]) : "l"(hin + 8 * k + lane) : "memory");
                    asm volatile("ld.relaxed.gpu.global.v2.u32 {%0,%1}, [%2];" : "=r"(hv[20]), "=r"(hv[21]) : "l"(reinterpret_cast<const uint2*>(hin + 160) + t) : "memory");
                    uint32_t m = max(hv[20], hv[21]);
#pragma unroll
                    for (int k = 0; k < 20; k += 2) m = __vimax3_u32(m, hv[k], hv[k + 1]);
                    if (!__any_sync(~0u, m == ~0u)) break;
                }
            }
            if (tid == 0) mbar_arrive(bars + 144);
            if (lane == 0) DBGC(52 - 16 * wg);
#pragma unroll
            for (int j = 0; j < 10; j++) {
                kp[j] = hv[j];
                asm volatile("movmatrix.sync.aligned.m8n8.trans.b16 %0, %1;" : "=r"(vp[j]) : "r"(hv[10 + j]));
            }
            if (up0) rk[0] = __uint_as_float(hv[20]);
            if (up1) rk[1] = __uint_as_float(hv[21]);
        };
        rk[2] = rw[2 * t + (up0 ? 0 : 8)].y; rk[3] = rw[2 * t + 1 + (up1 ? 0 : 8)].y;
        uint32_t qs[4][2];
#pragma unroll
        for (int h = 0; h < 4; h++) {
            qs[h][0] = (t >> 1) == (h & 1) ? f[0][5 * (h >> 1) + 2] : 0u; qs[h][1] = (t >> 1) == (h & 1) ? f[1][5 * (h >> 1) + 2] : 0u;
            asm volatile("" : "+r"(qs[h][0]), "+r"(qs[h][1]));
        }
#pragma unroll
        for (int j = 0; j < 10; j++) asm volatile("" : "+r"(f[0][j]), "+r"(f[1][j]), "+r"(f[0][10 + j]));
        if (warp & 3) above(); else if (wg) halo();
        TSTAMP1T(10, 64); CSA(2);
        if (warp && !wg) mbar_wait(bars + 416 + 8 * warp, 0);
        CSA(3);
        float sc[4][3][4];
#pragma unroll
        for (int h = 0; h < 4; h++) {
            const int jb = 5 * (h >> 1) + 3 * (h & 1), js = 5 * (h >> 1) + 2;
#pragma unroll
            for (int nt = 1; nt < 3; nt++) {
#pragma unroll
                for (int e = 0; e < 4; e++) sc[h][nt][e] = 0.f;
                mma_bf16(sc[h][nt], f[0][jb], f[1][jb], f[0][jb + 1], f[1][jb + 1], f[nt - 1][10 + jb], f[nt - 1][11 + jb]);
                mma_bf16_k8(sc[h][nt], qs[h][0], qs[h][1], f[nt - 1][10 + js]);
            }
        }
        if (warp == 0) halo();
        TSTAMP1(8); CSA(4);
#pragma unroll
        for (int h = 0; h < 4; h++) {
            const int jb = 5 * (h >> 1) + 3 * (h & 1), js = 5 * (h >> 1) + 2;
#pragma unroll
            for (int e = 0; e < 4; e++) sc[h][0][e] = 0.f;
            mma_bf16(sc[h][0], f[0][jb], f[1][jb], f[0][jb + 1], f[1][jb + 1], kp[jb], kp[jb + 1]);
            mma_bf16_k8(sc[h][0], qs[h][0], qs[h][1], kp[js]);
        }
        TSTAMP1T(3, 64);
        float p[4][4], sum[4][2];
        uint32_t lg[4][2], mx[4];
        const float rl[4] = {rk[0] * ra, rk[1] * ra, rk[2] * rb, rk[3] * rb};
        auto max2 = [](uint32_t a, uint32_t b) { uint32_t r; asm("max.bf16x2 %0, %1, %2;" : "=r"(r) : "r"(a), "r"(b)); return r; };
#pragma unroll
        for (int h = 0; h < 4; h++) {
            lg[h][0] = pack2((up0 ? sc[h][0][0] : sc[h][1][0]) * rl[0], (up0 ? sc[h][1][2] : sc[h][2][2]) * rl[2]);
            lg[h][1] = pack2((up1 ? sc[h][0][1] : sc[h][1][1]) * rl[1], (up1 ? sc[h][1][3] : sc[h][2][3]) * rl[3]);
            if (edge) {
                if (up0) lg[h][0] = __byte_perm(lg[h][0], 0xce6eu, 0x3254);
                if (up1) lg[h][1] = __byte_perm(lg[h][1], 0xce6eu, 0x3254);
            }
            mx[h] = max2(lg[h][0], lg[h][1]);
        }
#pragma unroll
        for (int o = 1; o <= 2; o <<= 1)
#pragma unroll
            for (int h = 0; h < 4; h++) mx[h] = max2(mx[h], __shfl_xor_sync(~0u, mx[h], o));
#pragma unroll
        for (int h = 0; h < 4; h++)
#pragma unroll
            for (int r = 0; r < 2; r++) {
                const float m = __uint_as_float(r ? mx[h] & 0xffff0000u : mx[h] << 16);
#pragma unroll
                for (int e = 0; e < 2; e++)
                    asm("ex2.approx.ftz.f32 %0, %1;" : "=f"(p[h][2 * r + e]) : "f"((__uint_as_float(r ? lg[h][e] & 0xffff0000u : lg[h][e] << 16) - m) * 1.4426950408889634f));
                sum[h][r] = p[h][2 * r] + p[h][2 * r + 1];
            }
#pragma unroll
        for (int o = 1; o <= 2; o <<= 1)
#pragma unroll
            for (int h = 0; h < 4; h++)
#pragma unroll
                for (int r = 0; r < 2; r++) sum[h][r] += __shfl_xor_sync(~0u, sum[h][r], o);
        TSTAMP1T(5, 64); CSA(5);
        const uint32_t mu = (up0 ? 0xffffu : 0u) | (up1 ? 0xffff0000u : 0u);
        uint32_t ob[10][2];
#pragma unroll
        for (int P = 0; P < 2; P++) {
            float os[2][4];
#pragma unroll
            for (int e = 0; e < 2; e++) {
                const int h = 2 * P + e;
                const float i0 = rcp_apx(sum[h][0]), i1 = rcp_apx(sum[h][1]);
                const uint32_t w0 = pack2(p[h][0] * rk[0] * i0, p[h][1] * rk[1] * i0), w1 = pack2(p[h][2] * rk[2] * i1, p[h][3] * rk[3] * i1);
#pragma unroll
                for (int dt = 0; dt < 3; dt++) {
                    const int j = 5 * P + (dt < 2 ? 3 * e + dt : 2);
                    float o[4] = {0.f, 0.f, 0.f, 0.f};
                    mma_bf16(o, w0 & ~mu, w1 & mu, 0u, w1 & ~mu, vb[j][0], vb[j][1]);
                    mma_bf16_k8(o, w0 & mu, 0u, vp[j]);
                    if (dt < 2) { ob[j][0] = pack2(o[0], o[1]); ob[j][1] = pack2(o[2], o[3]); }
                    else { os[e][0] = o[0]; os[e][1] = o[1]; os[e][2] = o[2]; os[e][3] = o[3]; }
                }
            }
#pragma unroll
            for (int k = 0; k < 4; k++) os[0][k] = t < 2 ? os[0][k] : os[1][k];
            ob[5 * P + 2][0] = pack2(os[0][0], os[0][1]); ob[5 * P + 2][1] = pack2(os[0][2], os[0][3]);
        }
        const uint32_t sl = sbase + (wg ? A1_SM_A1 : A1_SM_A0);
        const uint32_t o0 = (warp & 3) * 2048 + g * 64 + ((t ^ (g >> 1)) << 4), o1 = 8192 + (warp & 3) * 512 + g * 32 + ((t ^ ((g >> 2) << 1)) << 3);
        CSA(15);
        mbar_wait(bar_done, 0);
        if (wg == 0) mbar_wait(bar_kvf, 0);
#pragma unroll
        for (int h = 0; h < 2; h++) {
            asm volatile("st.shared.v4.u32 [%0], {%1,%2,%3,%4};" ::"r"(sl + o0 + h * 1024), "r"(ob[0][h]), "r"(ob[1][h]), "r"(ob[2][h]), "r"(ob[3][h]) : "memory");
            asm volatile("st.shared.v4.u32 [%0], {%1,%2,%3,%4};" ::"r"(sl + o0 + h * 1024 + 512), "r"(ob[4][h]), "r"(ob[5][h]), "r"(ob[6][h]), "r"(ob[7][h]) : "memory");
            asm volatile("st.shared.v2.u32 [%0], {%1,%2};" ::"r"(sl + o1 + h * 256), "r"(ob[8][h]), "r"(ob[9][h]) : "memory");
        }
        if (wg && lane == 0) mbar_arrive(bars + 384 + 8 * warp);
        fence_async_smem();
        __syncwarp();
        TSTAMP1T(4, 64); CSA(6);
        TSTAMP1(1);
        TSTAMP2(1);
        const unsigned char* ot = reinterpret_cast<const unsigned char*>(of) + mb * 163840 + wg * 10240;
        if (lane == 0) {
            asm volatile("cp.async.bulk.global.shared::cta.bulk_group [%0], [%1], 2048;" ::"l"(ot + hg * 20480 + (warp & 3) * 2048), "r"(sl + (warp & 3) * 2048) : "memory");
            asm volatile("cp.async.bulk.global.shared::cta.bulk_group [%0], [%1], 512;" ::"l"(ot + hg * 20480 + 8192 + (warp & 3) * 512), "r"(sl + 8192 + (warp & 3) * 512) : "memory");
            asm volatile("cp.async.bulk.commit_group;" ::: "memory");
            if (wg == 0) mbar_arrive(bar_pv);
            asm volatile("cp.async.bulk.wait_group 0;" ::: "memory");
            asm volatile(A1_FRED " [%0], 1;" ::"l"(reinterpret_cast<uint32_t*>(rsum + 2 * SEQ) + (((layer * 16 + mb) * 2 + wg) * 8 + hg) * FSTR) : "memory");
            DBGC(4 + warp);
        }
        TSTAMP4(11); CSA(7);
        float ac2[40];
        const uint64_t db0 = make_desc(sbase, 1024, 256, 3), db1 = make_desc(sbase + 10240, 512, 256, 3), da0 = make_desc(sl, 16, 1024, 2), da1 = make_desc(sl + 8192, 16, 256, 3);
        const uint32_t o7 = wg ? 640 : (A1_SM_W0 - A1_SM_A0) >> 4;
        const uint32_t trow = ((lane & 7) + 8 * (lane >> 4)) * 128 + (((2 * (warp & 3) + ((lane >> 3) & 1)) ^ (lane & 7)) << 4);
        uint32_t xr[10][2];
        mbar_wait(bar_f2 + 64 * wg + 64, 0);
        if (layer == 0) {
#pragma unroll
            for (int j = 0; j < 10; j += 2) ldsm_x4(&xr[j][0], sl + 51200 + (16 * (warp & 3) + (lane & 15)) * 160 + (lane >> 4) * 16 + 16 * j);
        } else {
#pragma unroll
            for (int j = 0; j < 10; j += 2) ldsm_x4_t(&xr[j][0], sl + 51200 + trow + 1024 * j);
        }
        const uint32_t ri = __shfl_sync(~0u, layer * SEQ + (wg * 2 + ((g >> 1) & 1)) * 512 + (mb * 16 + 4 * (warp & 3) + (g >> 2)) * 2 + (g & 1), lane);
        mbar_wait(bar_wo, 0);
        if (wg) mbar_wait(bar_pv, 0);
        if (wg) asm volatile("bar.sync 2, 128;" ::: "memory"); else asm volatile("bar.sync 1, 128;" ::: "memory");
        TSTAMP2(2); CSA(8);
#pragma unroll
        for (int q = 0; q < 8; q++) {
            uint32_t bo = wo_off(0) >> 4;
            if (q) {
                mbar_wait(bar_f2 + 64 * wg + 8 * q, 0);
                asm volatile("ld.shared.u32 %0, [%1];" : "=r"(bo) : "r"(que + 32 * wg + 4 * q) : "memory");
                bo = __shfl_sync(~0u, bo, 0);
                TSTAMP4(q);
                if (q % 3 == 1) CSA(9 + q / 3);
                if (q == 1 && (tid & 127) == 0) DBGC(29 + 8 * wg);
            }
            wgmma_fence();
#pragma unroll
            for (int j = 0; j < 5; j++) wgmma_n80(ac2, (j < 4 ? da0 : da1) + (q == 7 ? o7 : 0u) + (uint64_t)((q < 6 ? q * 640 : 0) + (j & 2) * 16 + (j & 1) * 2), (j < 4 ? db0 : db1) + bo + (uint64_t)((j & 2) * 160 + (j & 1) * 32), j || q);
            wgmma_commit();
            if (q == 0) {
                wgmma_wait<0>();
                if ((tid & 127) == 0) { mbar_arrive(bar_e2 + 16 * wg); mbar_arrive(bar_e2 + 8); }
            }
            if (q == 2 && wg) {
                wgmma_wait<1>();
                if (tid == 128) mbar_arrive(bar_e2 + 24);
            }
        }
        if ((tid & 127) == 0) DBGC(28 + wg * 8 + 7);
        TSTAMP2(3);
        wgmma_wait<0>();
        TSTAMP2(4); CSA(12);
        if (__any_sync(~0u, ac2[0] != ac2[0] || ac2[2] != ac2[2])) {
#pragma unroll
            for (int i = 0; i < 40; i++) ac2[i] = 0.f;
            uint32_t a[20], an[20];
            auto lda = [&](uint32_t (&r)[20], int h) {
#pragma unroll
                for (int u = 0; u < 4; u++)
                    asm volatile("ld.relaxed.gpu.global.v4.u32 {%0,%1,%2,%3}, [%4];" : "=r"(r[4 * u]), "=r"(r[4 * u + 1]), "=r"(r[4 * u + 2]), "=r"(r[4 * u + 3]) : "l"(ot + h * 20480 + o0 + u * 512) : "memory");
#pragma unroll
                for (int u = 0; u < 2; u++)
                    asm volatile("ld.relaxed.gpu.global.v2.u32 {%0,%1}, [%2];" : "=r"(r[16 + 2 * u]), "=r"(r[17 + 2 * u]) : "l"(ot + h * 20480 + o1 + u * 256) : "memory");
            };
            lda(an, 0);
#pragma unroll 5
            for (int k = lane; k < WOB / 16; k += 32)
                reinterpret_cast<uint4*>(stg + (sl - sbase))[k] = __ldcg(reinterpret_cast<const uint4*>(wo + hg * 8 * WOB) + k);
            __syncwarp();
#pragma unroll 1
            for (int h = 0; h < 8; h++) {
#pragma unroll 1
                for (int it = 0; it < SPIN_MAX; it++) {
                    uint32_t m = 0;
#pragma unroll
                    for (int k = 0; k < 20; k += 2) m = __vimax3_u32(m, an[k], an[k + 1]);
                    if (!__any_sync(~0u, m == ~0u)) break;
                    lda(an, h);
                }
#pragma unroll
                for (int k = 0; k < 20; k++) a[k] = an[k];
                lda(an, min(h + 1, 7));
                const uint32_t bp = h == hg ? sl : sbase + wo_off(h + (h < hg));
                const int r0 = 8 * ((lane & 7) >> 1) + 2 * (lane >> 3) + (lane & 1), r2 = 4 * ((lane & 7) >> 1) + 2 * ((lane >> 3) & 1) + (lane & 1);
#pragma unroll
                for (int n = 0; n < 10; n++) {
                    uint32_t b[12];
                    ldsm_x4_t(b, bp + (n >> 1) * 1024 + r0 * 32 + (((n ^ (r0 >> 2)) & 1) << 4));
                    ldsm_x4_t(b + 4, bp + 5120 + (n >> 1) * 1024 + r0 * 32 + (((n ^ (r0 >> 2)) & 1) << 4));
                    ldsm_x4_t(b + 8, bp + 10240 + (n >> 1) * 512 + r2 * 32 + (((n ^ (r2 >> 2)) & 1) << 4));
                    mma_bf16(ac2 + 4 * n, a[0], a[8], a[1], a[9], b[0], b[1]); mma_bf16(ac2 + 4 * n, a[2], a[10], a[3], a[11], b[2], b[3]);
                    mma_bf16(ac2 + 4 * n, a[4], a[12], a[5], a[13], b[4], b[5]); mma_bf16(ac2 + 4 * n, a[6], a[14], a[7], a[15], b[6], b[7]);
                    mma_bf16(ac2 + 4 * n, a[16], a[18], a[17], a[19], b[8], b[9]);
                }
            }
        }
#pragma unroll
        for (int j = 0; j < 10; j++)
#pragma unroll
            for (int hh = 0; hh < 2; hh++) {
                const uint32_t a = pack2(ac2[4 * j + 2 * hh], ac2[4 * j + 2 * hh + 1]);
                const __nv_bfloat162 r = __hadd2_rn(*reinterpret_cast<const __nv_bfloat162*>(&xr[j][hh]), *reinterpret_cast<const __nv_bfloat162*>(&a));
                xr[j][hh] = *reinterpret_cast<const uint32_t*>(&r);
            }
        const uint32_t so = sl + 30720;
#pragma unroll
        for (int j = 0; j < 10; j += 2) stsm_x4_t(so + trow + 1024 * j, xr[j][0], xr[j][1], xr[j + 1][0], xr[j + 1][1]);
        fence_async_smem();
        if (wg) asm volatile("bar.sync 2, 128;" ::: "memory"); else asm volatile("bar.sync 1, 128;" ::: "memory");
        TSTAMP2(5); CSA(13);
        if ((tid & 127) == 0) {
            asm volatile("cp.async.bulk.tensor.2d.global.shared::cta.bulk_group [%0, {%1, %2}], [%3];" ::"l"(&tmX1), "r"(mb * 128 + 64 * wg), "r"(hg * 80), "r"(so) : "memory");
            asm volatile("cp.async.bulk.commit_group;" ::: "memory");
        }
        __syncwarp();
        const float p0 = *(volatile const float*)&rw[g].x, p1 = *(volatile const float*)&rw[g + 8].x;
        float s[3][4] = {};
        const uint32_t pp[2] = {__byte_perm(__float_as_uint(p0), 0, 0x3232), __byte_perm(__float_as_uint(p1), 0, 0x3232)};
#pragma unroll
        for (int j = 0; j < 10; j += 2) {
            const uint32_t d0 = sub2(xr[j][0], pp[0]), d1 = sub2(xr[j][1], pp[1]), d2 = sub2(xr[j + 1][0], pp[0]), d3 = sub2(xr[j + 1][1], pp[1]);
            mma_bf16(s[0], xr[j][0], xr[j][1], xr[j + 1][0], xr[j + 1][1], 0x3f803f80u, 0x3f803f80u);
            mma_bf16(s[1], d0, d1, d2, d3, d0, d2);
            mma_bf16(s[2], d0, d1, d2, d3, d1, d3);
        }
        if (t == (g >> 1)) {
            float2* rp = rsum + ri;
            asm volatile("red.relaxed.gpu.global.add.v2.f32 [%0], {%1, %2};" ::"l"(rp), "f"(fmaf(-80.f, p0, s[0][0])), "f"((g & 1) ? s[1][1] : s[1][0]) : "memory");
            asm volatile("red.relaxed.gpu.global.add.v2.f32 [%0], {%1, %2};" ::"l"(rp + 4), "f"(fmaf(-80.f, p1, s[0][2])), "f"((g & 1) ? s[2][3] : s[2][2]) : "memory");
        }
        asm volatile("cp.async.bulk.wait_group.read 0;" ::: "memory");
        TSTAMP2(6); CSA(14); CSA_END;
        if (tid == 0) DBGC(63);
        if (tid == 128) DBGC(28);
        if (tid == 0) DBGCAL(2);
        GSTAMP(g_tim1, 14);
        SPAN(1 + 4 * layer, 3);
    }
}

static int h_nsm;
static void* h_sym[11];
static TileTab h_tab;
static CUtensorMap h_tmX0, h_tmX1, h_tmR0, h_tmR1, h_tmX1st, h_tmOut, h_tmWq, h_tmWo, h_tmWt;
typedef CUresult (*PFN_encodeTiled)(CUtensorMap*, CUtensorMapDataType, cuuint32_t, void*, const cuuint64_t*, const cuuint64_t*,
                                    const cuuint32_t*, const cuuint32_t*, CUtensorMapInterleave, CUtensorMapSwizzle,
                                    CUtensorMapL2promotion, CUtensorMapFloatOOBfill);
static void make_tmap(CUtensorMap* tm, const void* ptr, uint64_t cols, uint64_t rows, uint32_t bc, uint32_t br, CUtensorMapSwizzle sw, uint64_t pitch = 0, uint64_t hi = 0, uint32_t bh = 2) {
    static PFN_encodeTiled fn = nullptr;
    if (!fn) {
        void* p = nullptr; cudaDriverEntryPointQueryResult qr;
        cudaGetDriverEntryPoint("cuTensorMapEncodeTiled", &p, cudaEnableDefault, &qr);
        fn = (PFN_encodeTiled)p;
    }
    if (br == 0) {
        cuuint64_t dims[5] = {16, 2, rows / 8, 4, cols / 16}; cuuint64_t strides[4] = {cols * 2, cols * 16, cols * 4, 32};
        cuuint32_t box[5] = {16, 2, bc, 4, 5}; cuuint32_t es[5] = {1, 1, 1, 1, 1};
        fn(tm, CU_TENSOR_MAP_DATA_TYPE_BFLOAT16, 5, const_cast<void*>(ptr), dims, strides, box, es, CU_TENSOR_MAP_INTERLEAVE_NONE, sw,
           CU_TENSOR_MAP_L2_PROMOTION_L2_128B, CU_TENSOR_MAP_FLOAT_OOB_FILL_NONE);
        return;
    }
    if (bh == 0) {
        cuuint64_t dims[5] = {64, 64, 2, 16, 10}; cuuint64_t strides[4] = {pitch * 2, hi * 2, cols * 2, rows * 2};
        cuuint32_t box[5] = {64, 64, 2, 1, 1}; cuuint32_t es[5] = {1, 1, 1, 1, 1};
        fn(tm, CU_TENSOR_MAP_DATA_TYPE_BFLOAT16, 5, const_cast<void*>(ptr), dims, strides, box, es, CU_TENSOR_MAP_INTERLEAVE_NONE, sw,
           CU_TENSOR_MAP_L2_PROMOTION_L2_128B, CU_TENSOR_MAP_FLOAT_OOB_FILL_NONE);
        return;
    }
    if (hi) {
        cuuint64_t dims[3] = {cols, rows, hi == 64 ? 32u : hi == 16 ? 120u : 2u}; cuuint64_t strides[2] = {pitch * 2, hi * 2};
        cuuint32_t box[3] = {bc, br, bh}; cuuint32_t es[3] = {1, 1, 1};
        fn(tm, CU_TENSOR_MAP_DATA_TYPE_BFLOAT16, 3, const_cast<void*>(ptr), dims, strides, box, es, CU_TENSOR_MAP_INTERLEAVE_NONE, sw,
           CU_TENSOR_MAP_L2_PROMOTION_L2_128B, CU_TENSOR_MAP_FLOAT_OOB_FILL_NONE);
        return;
    }
    cuuint64_t dims[2] = {cols, rows}; cuuint64_t strides[1] = {(pitch ? pitch : cols) * 2};
    cuuint32_t box[2] = {bc, br}; cuuint32_t es[2] = {1, 1};
    fn(tm, CU_TENSOR_MAP_DATA_TYPE_BFLOAT16, 2, const_cast<void*>(ptr), dims, strides, box, es, CU_TENSOR_MAP_INTERLEAVE_NONE, sw,
       CU_TENSOR_MAP_L2_PROMOTION_L2_128B, CU_TENSOR_MAP_FLOAT_OOB_FILL_NONE);
}
template <typename... Args>
static void launch_pdl(void (*kern)(Args...), int grid, int block, int smem, Args... args) {
    cudaLaunchConfig_t cfg = {};
    cfg.gridDim = dim3(grid); cfg.blockDim = dim3(block); cfg.dynamicSmemBytes = smem; cfg.stream = cudaStreamPerThread;
    cudaLaunchAttribute at[1];
    at[0].id = cudaLaunchAttributeProgrammaticStreamSerialization; at[0].val.programmaticStreamSerializationAllowed = 1;
    cfg.attrs = at; cfg.numAttrs = 1;
    cudaLaunchKernelEx(&cfg, kern, args...);
}
static void launch_stage(int k, void* const* d_in, void* d_out) {
    const KgIn kg = {(const bf16*)d_in[4], (const bf16*)d_in[5], (const bf16*)d_in[6], (const bf16*)d_in[7], (const bf16*)d_in[8], (const bf16*)d_in[9], (const bf16*)d_in[0], (const bf16*)d_in[1], (const bf16*)d_in[2],
                      (uint4*)h_sym[0], (uint4*)h_sym[1], (uint4*)h_sym[2], (uint4*)h_sym[3], (uint4*)h_sym[4], (float*)h_sym[5]};
    switch (k) {
        case 0: kgen_kernel<<<128, 512, KG_SMEM, cudaStreamPerThread>>>(kg, h_tmWq, h_tmWo, h_tmWt); break;
        case 1: launch_pdl(a1_kernel, h_nsm, A1_THREADS, A1_SMEM, 0, (const bf16*)d_in[0], (const unsigned char*)h_sym[1], (const unsigned char*)h_sym[2], (float2*)h_sym[4], (uint4*)h_sym[6], h_tmX0, h_tmR0, h_tmX1st, h_tab); break;
        case 3: launch_pdl(conv_kernel, DM / CV_CPB, CV_THREADS, CV_SMEM, 0, (const uint4*)h_sym[7], (const float4*)h_sym[4], (const bf16*)h_sym[8], (bf16*)h_sym[9], (const uint4*)h_sym[0], h_tmOut); break;
        case 5: launch_pdl(a1_kernel, h_nsm, A1_THREADS, A1_SMEM, 1, (const bf16*)d_in[0], (const unsigned char*)h_sym[1], (const unsigned char*)h_sym[2], (float2*)h_sym[4], (uint4*)h_sym[6], h_tmX1, h_tmR1, h_tmX1st, h_tab); break;
        case 7: launch_pdl(conv_kernel, DM / CV_CPB, CV_THREADS, CV_SMEM, 1, (const uint4*)h_sym[7] + SEQ / 8, (const float4*)h_sym[4] + SEQ / 2, (const bf16*)h_sym[8], (bf16*)h_sym[10], (const uint4*)h_sym[0], h_tmOut); break;
        default: break;
    }
}
static int n_stage_kernels() { return 9; }
static const char* stage_name(int k) { const char* n[] = {"kgen", "a1", "a2", "conv", "tr", "a1", "a2", "conv", "tr"}; return n[k]; }

extern "C" void kernel_launch(void* const* d_in, const int* in_sizes, int n_in, void* d_out, int out_size) {
    (void)in_sizes; (void)n_in; (void)out_size;
    static const void *p_in = nullptr, *p_w1 = nullptr, *p_w2 = nullptr, *p_out = nullptr;
    if (p_in != d_in[0] || p_w1 != d_in[1] || p_w2 != d_in[2] || p_out != d_out) {
        cudaFuncSetAttribute(conv_kernel, cudaFuncAttributeMaxDynamicSharedMemorySize, CV_SMEM);
        cudaFuncSetAttribute(kgen_kernel, cudaFuncAttributeMaxDynamicSharedMemorySize, KG_SMEM);
        cudaFuncSetAttribute(a1_kernel, cudaFuncAttributeMaxDynamicSharedMemorySize, A1_SMEM);
        int dev; cudaGetDevice(&dev); cudaDeviceGetAttribute(&h_nsm, cudaDevAttrMultiProcessorCount, dev);
        if (h_nsm != 132) h_nsm = 128;
        h_tab.ns = h_nsm == 132 ? 132 : ~0u;
        for (int i = 0; i < 264; i++) {
            const int h = (i - 64) >> 1;
            const int t = i >= 132 ? i - 132 : i < 64 ? ((i >> 1) & 7) * 16 + (i >> 4) * 2 + (i & 1) : i < 120 ? (1 + h % 7) * 16 + 8 + (h / 7) * 2 + (i & 1) : i < 124 ? 128 : i - 116;
            const int hg = (4 * (t >> 6) + (t & 3)) & 7;
            h_tab.e[i] = {(unsigned char)((t >> 2) & 15), (unsigned char)hg, (unsigned char)(5 * (hg >> 2)), (unsigned char)t, (uint32_t)(hg * 10 * WQ_STAGE)};
        }
        cudaGetSymbolAddress(&h_sym[0], g_tap); cudaGetSymbolAddress(&h_sym[1], g_wq); cudaGetSymbolAddress(&h_sym[2], g_wo);
        cudaGetSymbolAddress(&h_sym[3], g_halo); cudaGetSymbolAddress(&h_sym[4], g_sum); cudaGetSymbolAddress(&h_sym[5], g_csp); cudaGetSymbolAddress(&h_sym[6], g_of);
        cudaGetSymbolAddress(&h_sym[7], g_piv); cudaGetSymbolAddress(&h_sym[8], g_x1T); cudaGetSymbolAddress(&h_sym[9], g_xcT); cudaGetSymbolAddress(&h_sym[10], g_yT);
        void *px1, *px2;
        cudaGetSymbolAddress(&px1, g_x1T); cudaGetSymbolAddress(&px2, g_xcT);
        make_tmap(&h_tmX0, d_in[0], 128 * 640, 64, 64, 64, CU_TENSOR_MAP_SWIZZLE_128B, 1280, 640, 0);
        make_tmap(&h_tmX1, px2, 128, 64 * XCP, 64, 64, CU_TENSOR_MAP_SWIZZLE_128B, XCP, 64, 0);
        make_tmap(&h_tmR0, d_in[0], 640, 1024, 80, 64, CU_TENSOR_MAP_SWIZZLE_NONE, 1280, 640, 1);
        make_tmap(&h_tmR1, px2, 64, 640, 64, 80, CU_TENSOR_MAP_SWIZZLE_128B, XCP, 64, 1);
        make_tmap(&h_tmX1st, px1, 2048, 640, 64, 80, CU_TENSOR_MAP_SWIZZLE_128B, XCP);
        make_tmap(&h_tmWq, d_in[1], 16, 640, 16, 32, CU_TENSOR_MAP_SWIZZLE_32B, 1920, 16, 5);
        make_tmap(&h_tmWo, d_in[2], 640, 640, 4, 0, CU_TENSOR_MAP_SWIZZLE_32B);
        make_tmap(&h_tmWt, d_in[2], 640, 640, 2, 0, CU_TENSOR_MAP_SWIZZLE_32B);
        make_tmap(&h_tmOut, d_out, 640, 1024, 80, 8, CU_TENSOR_MAP_SWIZZLE_NONE, 1280, 640, 1);
        p_in = d_in[0]; p_w1 = d_in[1]; p_w2 = d_in[2]; p_out = d_out;
    }
    for (int k = 0; k < n_stage_kernels(); k++) launch_stage(k, d_in, d_out);
}
```

```cpp
#include <cuda_runtime.h>
#include <cuda_bf16.h>
#include <stdint.h>
#include <cuda.h>

typedef __nv_bfloat16 bf16;

constexpr int SEQ = 2048;
constexpr int DM = 640;
constexpr int NMODE = 192;

__device__ __forceinline__ float bf2f(bf16 v) { return __bfloat162float(v); }
__device__ __forceinline__ float rbf(float v) {
    uint32_t r;
    asm("cvt.rn.bf16x2.f32 %0, %1, %2;" : "=r"(r) : "f"(v), "f"(0.f));
    return __uint_as_float(r);
}
__device__ __forceinline__ uint32_t pack2(float lo, float hi) {
    __nv_bfloat162 t = __floats2bfloat162_rn(lo, hi);
    return *reinterpret_cast<uint32_t*>(&t);
}
__device__ __forceinline__ void pdl_sync() {
    asm volatile("griddepcontrol.wait;" ::: "memory");
    asm volatile("griddepcontrol.launch_dependents;" ::: "memory");
}
__device__ __forceinline__ float sqrt_apx(float v) { float r; asm("sqrt.approx.ftz.f32 %0, %1;" : "=f"(r) : "f"(v)); return r; }
__device__ __forceinline__ float rcp_apx(float v) { float r; asm("rcp.approx.ftz.f32 %0, %1;" : "=f"(r) : "f"(v)); return r; }
__device__ __forceinline__ uint32_t smem_u32(const void* p) { return (uint32_t)__cvta_generic_to_shared(p); }

constexpr int TAPB = 2 * 152 * 8;
__device__ __align__(128) uint4 g_tap[DM * 128];
#define XPAD 64
constexpr int XCP = SEQ + XPAD;
__device__ __align__(128) bf16 g_x1T[DM * XCP];
__device__ __align__(128) bf16 g_xcT[DM * XCP];
__device__ __align__(128) uint4 g_of[128 * 1280];
constexpr int WQ_STAGE = 240 * 128, WOB = 80 * 160;
__device__ __align__(128) uint4 g_wq[8 * 10 * WQ_STAGE / 16];
__device__ __align__(128) uint4 g_wo[64 * WOB / 16];
__device__ __align__(16) float g_csp[10 * 1920];
#define FSTR 32
__device__ __align__(128) float2 g_sum[2 * SEQ + 256 * FSTR];
__device__ __align__(16) bf16 g_piv[2 * SEQ];
__device__ __align__(128) bf16 g_yT[DM * XCP];
__device__ uint32_t g_epoch;
__device__ __align__(16) unsigned long long g_rstat[SEQ];
__device__ __align__(128) uint4 g_halo[640 * 148];
__device__ __forceinline__ unsigned long long tagw(uint32_t payload, uint32_t tag) { return ((unsigned long long)tag << 32) | payload; }
__device__ __forceinline__ ulonglong2 ld_tag2(const ulonglong2* p) {
    ulonglong2 v;
    asm volatile("ld.relaxed.gpu.global.v2.u64 {%0, %1}, [%2];" : "=l"(v.x), "=l"(v.y) : "l"(p) : "memory");
    return v;
}
__device__ __forceinline__ bool tag_ok(ulonglong2 v, uint32_t tag) { return (uint32_t)(v.x >> 32) == tag && (uint32_t)(v.y >> 32) == tag; }
__device__ __forceinline__ uint32_t ld_epoch() { uint32_t v; asm volatile("ld.relaxed.gpu.global.u32 %0, [%1];" : "=r"(v) : "l"(&g_epoch) : "memory"); return v + 1; }
constexpr int SPIN_MAX = 1 << 20;
__device__ uint32_t g_started[4];
__device__ __forceinline__ void sm_started(int slot) { asm volatile("red.relaxed.gpu.global.add.u32 [%0], 1;" ::"l"(g_started + slot) : "memory"); }
__device__ __noinline__ void sm_idle(int slot) {
    if (threadIdx.x) return;
    sm_started(slot);
    const uint32_t want = ld_epoch() * gridDim.x;
    pdl_sync();
#pragma unroll 1
    for (int it = 0; it < SPIN_MAX; it++) {
        uint32_t v;
        asm volatile("ld.relaxed.gpu.global.u32 %0, [%1];" : "=r"(v) : "l"(g_started + slot) : "memory");
        if ((int)(v - want) >= 0) break;
        __nanosleep(100);
    }
}
struct TileTab { uint4 e[132]; };
__device__ __forceinline__ bool elect() {
    uint32_t p;
    asm volatile("{\n.reg .pred p;\nelect.sync _|p, 0xffffffff;\nselp.b32 %0, 1, 0, p;\n}" : "=r"(p));
    return p;
}
#define DBG_SYMS
#define TSTAMP(i)
#define TSTAMP1(i)
#define TSTAMP1T(i, t)
#define TSTAMP1X(i, t)
#define SPAN(k, i)
#define GSTAMP(arr, i)
#define TSTAMP2(i)
#define TSTAMP3(i)
#define TSTAMP4(i)
#define TSTAMPK(i, t)
#define TSTAMPC(i)
#define DBGC(i)
#define DBGV(i, v)
#define DBGCAL(i)

#define CSA(i)
#define CSA_END
#define CST(i)
#define CST_END
#define CST_EXTRA 0
__device__ __forceinline__ void mma_bf16(float* d, uint32_t a0, uint32_t a1, uint32_t a2, uint32_t a3, uint32_t b0, uint32_t b1) {
    asm volatile("mma.sync.aligned.m16n8k16.row.col.f32.bf16.bf16.f32 {%0,%1,%2,%3}, {%4,%5,%6,%7}, {%8,%9}, {%0,%1,%2,%3};"
                 : "+f"(d[0]), "+f"(d[1]), "+f"(d[2]), "+f"(d[3]) : "r"(a0), "r"(a1), "r"(a2), "r"(a3), "r"(b0), "r"(b1));
}
__device__ __forceinline__ void mma_bf16_k8(float* d, uint32_t a0, uint32_t a1, uint32_t b0) {
    asm volatile("mma.sync.aligned.m16n8k8.row.col.f32.bf16.bf16.f32 {%0,%1,%2,%3}, {%4,%5}, {%6}, {%0,%1,%2,%3};"
                 : "+f"(d[0]), "+f"(d[1]), "+f"(d[2]), "+f"(d[3]) : "r"(a0), "r"(a1), "r"(b0));
}
__device__ __forceinline__ void ldsm_x4(uint32_t* r, uint32_t addr) {
    asm volatile("ldmatrix.sync.aligned.m8n8.x4.shared.b16 {%0,%1,%2,%3}, [%4];"
                 : "=r"(r[0]), "=r"(r[1]), "=r"(r[2]), "=r"(r[3]) : "r"(addr));
}

__device__ __forceinline__ void ldsm_x4_t(uint32_t* r, uint32_t addr) {
    asm volatile("ldmatrix.sync.aligned.m8n8.x4.trans.shared.b16 {%0,%1,%2,%3}, [%4];"
                 : "=r"(r[0]), "=r"(r[1]), "=r"(r[2]), "=r"(r[3]) : "r"(addr));
}
__device__ __forceinline__ void mbar_init(uint32_t bar, int count) { asm volatile("mbarrier.init.shared::cta.b64 [%0], %1;" ::"r"(bar), "r"(count)); }
__device__ __forceinline__ void mbar_arrive(uint32_t bar) { asm volatile("mbarrier.arrive.shared::cta.b64 _, [%0];" ::"r"(bar) : "memory"); }
__device__ __forceinline__ void mbar_wait(uint32_t bar, uint32_t parity) {
    asm volatile("{\n.reg .pred p;\nWAIT_LOOP:\n"
                 "mbarrier.try_wait.parity.shared::cta.b64 p, [%0], %1;\n"
                 "@p bra.uni WAIT_DONE;\nbra.uni WAIT_LOOP;\nWAIT_DONE:\n}" ::"r"(bar), "r"(parity) : "memory");
}

__device__ __forceinline__ void mbar_expect_tx(uint32_t bar, uint32_t bytes) {
    asm volatile("mbarrier.arrive.expect_tx.shared::cta.b64 _, [%0], %1;" ::"r"(bar), "r"(bytes) : "memory");
}
__device__ __forceinline__ void tma_load_2d(uint32_t dst, const void* tmap, int c0, int c1, uint32_t bar) {
    asm volatile("cp.async.bulk.tensor.2d.shared::cluster.global.mbarrier::complete_tx::bytes [%0], [%1, {%3, %4}], [%2];"
                 ::"r"(dst), "l"(tmap), "r"(bar), "r"(c0), "r"(c1) : "memory");
}
__device__ __forceinline__ void tma_load_3d(uint32_t dst, const void* tmap, int c0, int c1, int c2, uint32_t bar) {
    asm volatile("cp.async.bulk.tensor.3d.shared::cluster.global.mbarrier::complete_tx::bytes [%0], [%1, {%3, %4, %5}], [%2];"
                 ::"r"(dst), "l"(tmap), "r"(bar), "r"(c0), "r"(c1), "r"(c2) : "memory");
}
__device__ __forceinline__ void fence_async_smem() { asm volatile("fence.proxy.async.shared::cta;" ::: "memory"); }
__device__ __forceinline__ void bulk_load(uint32_t dst, const void* src, uint32_t bytes, uint32_t bar) {
    asm volatile("cp.async.bulk.shared::cluster.global.mbarrier::complete_tx::bytes [%0], [%1], %2, [%3];"
                 ::"r"(dst), "l"(src), "r"(bytes), "r"(bar) : "memory");
}
__device__ __forceinline__ void stsm_x4(uint32_t addr, uint32_t r0, uint32_t r1, uint32_t r2, uint32_t r3) {
    asm volatile("stmatrix.sync.aligned.m8n8.x4.shared.b16 [%0], {%1,%2,%3,%4};" ::"r"(addr), "r"(r0), "r"(r1), "r"(r2), "r"(r3) : "memory");
}
__device__ __forceinline__ void stsm_x4_t(uint32_t addr, uint32_t r0, uint32_t r1, uint32_t r2, uint32_t r3) {
    asm volatile("stmatrix.sync.aligned.m8n8.x4.trans.shared.b16 [%0], {%1,%2,%3,%4};" ::"r"(addr), "r"(r0), "r"(r1), "r"(r2), "r"(r3) : "memory");
}
__device__ __forceinline__ void prefetch_tmap(const void* tmap) { asm volatile("prefetch.tensormap [%0];" ::"l"(tmap) : "memory"); }

__device__ __forceinline__ float2 cexp_at(float wr2, float wi, float p) {
    float er;
    asm("ex2.approx.ftz.f32 %0, %1;" : "=f"(er) : "f"(wr2 * p));
    float th = wi * p;
    const float k = rintf(th * 0.15915494309189535f);
    th = fmaf(k, -6.2831854820251465f, th);
    th = fmaf(k, 1.7484555314695172e-7f, th);
    return make_float2(er * __cosf(th), er * __sinf(th));
}
__device__ __forceinline__ float2 cmul(float2 a, float2 b) {
    return make_float2(fmaf(a.x, b.x, -a.y * b.y), fmaf(a.x, b.y, a.y * b.x));
}
__device__ __forceinline__ float2 csqr(float2 a) { return make_float2(fmaf(a.x, a.x, -a.y * a.y), (a.x + a.x) * a.y); }
__device__ __forceinline__ uint32_t packh(float2 v) {
    uint32_t r;
    asm("cvt.rn.f16x2.f32 %0, %1, %2;" : "=r"(r) : "f"(v.y), "f"(v.x));
    return r;
}
__device__ __forceinline__ void mma_f16(float* d, uint32_t a0, uint32_t a1, uint32_t a2, uint32_t a3, uint32_t b0, uint32_t b1) {
    asm volatile("mma.sync.aligned.m16n8k16.row.col.f32.f16.f16.f32 {%0,%1,%2,%3}, {%4,%5,%6,%7}, {%8,%9}, {%0,%1,%2,%3};"
                 : "+f"(d[0]), "+f"(d[1]), "+f"(d[2]), "+f"(d[3]) : "r"(a0), "r"(a1), "r"(a2), "r"(a3), "r"(b0), "r"(b1));
}

struct KgIn { const bf16 *logA, *Aim, *Cre, *Cim, *logdt, *dsk, *x, *wqkv, *wo; uint4 *tap, *wq, *wop, *halo, *sum; float* csp; };
constexpr int KG_THREADS = NMODE / 2;

constexpr int KG_BUF = 15 * 12288, KG_BAR = KG_BUF + 6 * 5120, KG_SMEM = KG_BAR + 64;
__global__ void __launch_bounds__(512, 1) kgen_kernel(const KgIn in, const __grid_constant__ CUtensorMap tmWq, const __grid_constant__ CUtensorMap tmWo,
                                                        const __grid_constant__ CUtensorMap tmWt) {
    extern __shared__ __align__(1024) uint4 tabs[];
#define KG_ROT 0
    const int lane = threadIdx.x & 31, w16 = (__shfl_sync(~0u, threadIdx.x >> 5, 0) + KG_ROT) & 15, grp = w16 / 3, warp = w16 - 3 * grp;
    const int d = blockIdx.x * 5 + grp, tid = warp * 32 + lane;
    uint4* tab = tabs + grp * (3 * 768);
    SPAN(0, 0); SPAN(0, 1);
    TSTAMPK(0, 0);
    asm volatile("griddepcontrol.launch_dependents;" ::: "memory");
    if (w16 == 15) {
        const uint32_t b0 = smem_u32(tab), wbar = b0 + 6 * 5120;
        const int blk = blockIdx.x, nq = blk < 112 ? 4 : 2, nj = nq + (blk < 64 ? 1 : 2);
        auto fetch = [&](int i) {
            const uint32_t dst = b0 + i * 5120, bar = wbar + 8 * i;
            if (i < nq) {
                const int p = blk + 64 * (i & 2), kb = p / 24;
                mbar_expect_tx(bar, 5120);
                tma_load_3d(dst, &tmWq, 0, kb * 64 + (i & 1) * 32, (p - 24 * kb) * 5, bar);
            } else if (i < nj) {
                const int o = i == nq ? blk : 255 - blk;
                mbar_expect_tx(bar, o < 128 ? 5120 : 2560);
                asm volatile("cp.async.bulk.tensor.5d.shared::cluster.global.mbarrier::complete_tx::bytes [%0], [%1, {%3, %3, %4, %3, %5}], [%2];"
                             ::"r"(dst), "l"(o < 128 ? &tmWo : &tmWt), "r"(bar), "r"(0), "r"((o & 7) * 10 + (o >> 6) * 4), "r"(((o >> 3) & 7) * 5) : "memory");
            }
        };
        const bool one = elect();
        if (one) {
#pragma unroll
            for (int i = 0; i < 6; i++) mbar_init(wbar + 8 * i, 1);
            asm volatile("fence.mbarrier_init.release.cluster;" ::: "memory");
#pragma unroll
            for (int i = 0; i < 6; i++) fetch(i);
        }
        __syncwarp();
#pragma unroll
        for (int i = 1; i <= 5; i++) asm volatile("bar.arrive %0, 128;" ::"r"(i) : "memory");
        if (one) {
#pragma unroll 1
            for (int i = 0; i < nj; i++) {
                const int p = blk + 64 * (i & 2), kb = p / 24, hg = p & 7, sec = (p - 24 * kb) >> 3, o = i == nq ? blk : 255 - blk, cg = (o >> 3) & 7, hb = o & 7;
                const unsigned char* dst = i < nq ? reinterpret_cast<unsigned char*>(in.wq) + (hg * 10 + (hg < 4 ? kb : kb < 5 ? kb + 5 : kb - 5)) * WQ_STAGE + ((i & 1) * 3 + sec) * 5120
                                                  : reinterpret_cast<unsigned char*>(in.wop) + (cg * 8 + (hb == cg ? 0 : hb + (hb < cg))) * WOB + (o >> 6) * 5120;
                mbar_wait(wbar + 8 * i, 0);
                if (i == 0) TSTAMPK(2, (15 - KG_ROT) * 32);
                if (i == 3) TSTAMPK(5, (15 - KG_ROT) * 32);
                asm volatile("cp.async.bulk.global.shared::cta.bulk_group [%0], [%1], %2;" ::"l"(dst), "r"(b0 + i * 5120), "r"(i < nq || o < 128 ? 5120 : 2560) : "memory");
            }
            asm volatile("cp.async.bulk.commit_group;" ::: "memory");
            asm volatile("cp.async.bulk.wait_group.read 0;" ::: "memory");
        }
        TSTAMPK(11, (15 - KG_ROT) * 32);
        return;
    }
    const bf16 pdt = in.logdt[d], pdsk = in.dsk[d];
    const uint32_t pla = reinterpret_cast<const uint32_t*>(in.logA)[d * KG_THREADS + tid], pai = reinterpret_cast<const uint32_t*>(in.Aim)[d * KG_THREADS + tid];
    const uint32_t pcr = reinterpret_cast<const uint32_t*>(in.Cre)[d * KG_THREADS + tid], pci = reinterpret_cast<const uint32_t*>(in.Cim)[d * KG_THREADS + tid];
    const bf16* pfq = tid < 30 ? in.wqkv + (size_t)(d * 30 + tid) * 64 : tid < 40 ? in.wo + (size_t)(d * 10 + tid - 30) * 64 : in.x + (size_t)(d * 32 + tid - 40) * 64;
#define KG_PF 0
    if (tid < (KG_PF == 3 ? 0 : KG_PF ? 40 : 72)) asm volatile("prefetch.global.L2 [%0];" ::"l"(pfq));
    asm volatile("st.global.v4.u32 [%0], {%1,%1,%1,%1};" ::"l"(in.halo + d * 148 + tid), "r"(~0u));
    if (tid < 52) asm volatile("st.global.v4.u32 [%0], {%1,%1,%1,%1};" ::"l"(in.halo + d * 148 + 96 + tid), "r"(~0u));
    else if (w16 == 2) {
        if (lane < 16) in.sum[blockIdx.x * 16 + lane] = make_uint4(0, 0, 0, 0);
        else if (lane < 20) reinterpret_cast<uint32_t*>(in.sum + 2048)[(blockIdx.x * 4 + lane - 16) * FSTR] = 0;
    }
    const uint32_t tw = smem_u32(tab) + warp * 12288;
    const int g = lane >> 2, t = lane & 3;
    const uint32_t sta = tw + lane * 128 + ((2 * (lane & 3) + ((lane >> 2) & 1)) << 4);
    const uint32_t lda = tw + t * 128 + ((g ^ (2 * t)) << 4);
    const uint32_t stb = tw + lane * 8, ldb = tw + g * 512 + (g & 3) * 32 + t * 8;
    auto sts4 = [&](int e, int off, uint32_t a, uint32_t b, uint32_t c, uint32_t dd) {
        asm volatile("st.shared.v4.u32 [%0], {%1,%2,%3,%4};" ::"r"((sta ^ (e << 4)) + off), "r"(a), "r"(b), "r"(c), "r"(dd) : "memory");
    };
    auto lds4 = [&](int sp, int off, uint32_t* r) {
        asm volatile("ld.shared.v4.u32 {%0,%1,%2,%3}, [%4];" : "=r"(r[0]), "=r"(r[1]), "=r"(r[2]), "=r"(r[3]) : "r"((lda ^ ((sp & 1) << 4)) + sp * 512 + off) : "memory");
    };
    const float dt = rbf(expf(bf2f(pdt)));
    float2 C[2], y1[2], z8[2], y128[2];
    float cmax = 0.f;
#pragma unroll
    for (int m = 0; m < 2; m++) {
        const float wr2 = -rbf(expf(__uint_as_float(m ? pla & 0xffff0000u : pla << 16))) * dt * 1.4426950408889634f;
        const float wi = __uint_as_float(m ? pai & 0xffff0000u : pai << 16) * dt;
        C[m] = make_float2(__uint_as_float(m ? pcr & 0xffff0000u : pcr << 16) * dt, -__uint_as_float(m ? pci & 0xffff0000u : pci << 16) * dt);
        cmax = fmaxf(cmax, fmaxf(fabsf(C[m].x), fabsf(C[m].y)));
        y1[m] = cexp_at(wr2, -wi, 1.f); z8[m] = cexp_at(wr2, wi, 8.f); y128[m] = cexp_at(wr2, -wi, 128.f);
    }
    const int ex = min(max((int)(__reduce_max_sync(~0u, __float_as_uint(cmax)) >> 23), 20), 240);
    const float scale = __uint_as_float((uint32_t)(127 + 10 + 127 - ex) << 23), unscale = 2.0f * __uint_as_float((uint32_t)(ex - 10) << 23);
    TSTAMPK(4, 64);
    if (KG_PF >= 2 && tid >= 40 && tid < 72) asm volatile("prefetch.global.L2 [%0];" ::"l"(pfq));
    float k2048 = 0.f;
    float acc[5][4];
#pragma unroll
    for (int j = 0; j < 5; j++)
#pragma unroll
        for (int k = 0; k < 4; k++) acc[j][k] = 0.f;
    uint32_t af[8][4];
    {
        float2 h0[2], h1[2], g0[2], g1[2], g2[2], g2b[2], g3[2], g4[2], y2[2], y4[2];
#pragma unroll
        for (int m = 0; m < 2; m++) {
            h0[m] = make_float2(1.f, 0.f); h1[m] = csqr(csqr(csqr(z8[m])));
            g0[m] = make_float2(C[m].x * scale, C[m].y * scale);
            g1[m] = cmul(g0[m], y128[m]);
            const float2 y256 = csqr(y128[m]), y512 = csqr(y256);
            g2b[m] = g2[m] = cmul(g0[m], y256); g3[m] = cmul(g0[m], y512); g4[m] = cmul(g3[m], y512);
            y2[m] = csqr(y1[m]); y4[m] = csqr(y2[m]);
            const float2 y1024 = csqr(y512);
            k2048 += fmaf(g4[m].x, y1024.x, -g4[m].y * y1024.y);
        }
#pragma unroll
        for (int e = 0; e < 8; e++) {
            sts4(e, 0, packh(h0[0]), packh(h1[0]), packh(h0[1]), packh(h1[1]));
            sts4(e, 4096, packh(g0[0]), packh(g0[1]), packh(g1[0]), packh(g1[1]));
#pragma unroll
            for (int m = 0; m < 2; m++)
                if (e < 7) { h0[m] = e ? cmul(h0[m], z8[m]) : z8[m]; h1[m] = cmul(h1[m], z8[m]); g0[m] = cmul(g0[m], y1[m]); g1[m] = cmul(g1[m], y1[m]); }
            if (e < 5) k2048 += __shfl_xor_sync(~0u, k2048, 1 << e);
        }
        if (KG_PF == 1 && tid >= 40 && tid < 72) asm volatile("prefetch.global.L2 [%0];" ::"l"(pfq));
        __syncwarp();
#pragma unroll
        for (int e = 0; e < 8; e++) {
            uint32_t b[4];
            lds4(e, 0, af[e]); lds4(e, 4096, b);
            sts4(e, 8192, packh(g2[0]), packh(g2[1]), packh((e & 1) ? cmul(g3[0], y4[0]) : g3[0]), packh((e & 1) ? cmul(g3[1], y4[1]) : g3[1]));
            asm volatile("st.shared.v2.u32 [%0], {%1,%2};" ::"r"((stb ^ ((e & 3) << 5)) + e * 512), "r"(packh(g4[0])), "r"(packh(g4[1])) : "memory");
#pragma unroll
            for (int m = 0; m < 2; m++)
                if (e < 7) {
                    g2[m] = e == 3 ? cmul(g2b[m], y128[m]) : cmul(g2[m], y2[m]);
                    if (e & 1) g3[m] = cmul(g3[m], y128[m]);
                    g4[m] = cmul(g4[m], y128[m]);
                }
            mma_f16(acc[0], af[e][0], af[e][1], af[e][2], af[e][3], b[0], b[1]);
            mma_f16(acc[1], af[e][0], af[e][1], af[e][2], af[e][3], b[2], b[3]);
        }
    }
    TSTAMPK(6, 64);
    __syncwarp();
#pragma unroll
    for (int sp = 0; sp < 8; sp++) {
        uint32_t c[4], e0, e1;
        lds4(sp, 8192, c);
        asm volatile("ld.shared.v2.u32 {%0,%1}, [%2];" : "=r"(e0), "=r"(e1) : "r"(ldb ^ (sp << 5)) : "memory");
        mma_f16(acc[2], af[sp][0], af[sp][1], af[sp][2], af[sp][3], c[0], c[1]);
        mma_f16(acc[3], af[sp][0], af[sp][1], af[sp][2], af[sp][3], c[2], c[3]);
        mma_f16(acc[4], af[sp][0], af[sp][1], af[sp][2], af[sp][3], e0, e1);
    }
    {
        float* Pp = reinterpret_cast<float*>(tab + warp * 768);
        auto sw = [](int i) { return i ^ ((i >> 2) & 24); };
#pragma unroll
        for (int h = 0; h < 2; h++) {
            const int b = g + 8 * h;
            *reinterpret_cast<float2*>(Pp + sw(8 * b + 2 * t)) = make_float2(acc[0][2 * h] * unscale, acc[0][2 * h + 1] * unscale);
            *reinterpret_cast<float2*>(Pp + 128 + sw(8 * b + 2 * t)) = make_float2(acc[1][2 * h] * unscale, acc[1][2 * h + 1] * unscale);
            *reinterpret_cast<float2*>(Pp + 256 + sw(4 * b + 2 * (t & 1) + 64 * (t >> 1))) = make_float2(acc[2][2 * h] * unscale, acc[2][2 * h + 1] * unscale);
            *reinterpret_cast<float2*>(Pp + 384 + sw(2 * b + 32 * t)) = make_float2(acc[3][2 * h] * unscale, acc[3][2 * h + 1] * unscale);
            Pp[512 + sw(b + 32 * t)] = acc[4][2 * h] * unscale;
            Pp[512 + sw(b + 32 * t + 16)] = acc[4][2 * h + 1] * unscale;
        }
        if (lane == 0) Pp[640] = k2048 * unscale;
    }
    TSTAMPK(7, 64);
    asm volatile("bar.sync %0, 128;" ::"r"(grp + 1) : "memory");
    TSTAMPK(9, 64);
    const float* Kp = reinterpret_cast<const float*>(tab);
    auto ksum = [&](int i) -> float { return (Kp[i] + Kp[3072 + i]) + Kp[6144 + i]; };
    auto ksum4 = [&](int q) -> float4 {
        q ^= (q >> 2) & 6;
        const float4 a = reinterpret_cast<const float4*>(Kp)[q], b = reinterpret_cast<const float4*>(Kp)[768 + q], c = reinterpret_cast<const float4*>(Kp)[1536 + q];
        return make_float4((a.x + b.x) + c.x, (a.y + b.y) + c.y, (a.z + b.z) + c.z, (a.w + b.w) + c.w);
    };
    {
        uint2* E4 = reinterpret_cast<uint2*>(in.tap + d * 128);
        float4 v = ksum4(tid), u = ksum4(96 + min(tid, 64));
        const float cor = rbf(ksum(tid == 95 ? 384 : 512));
        if (tid == 0) v.x += bf2f(pdsk);
        if (tid == 95) v.w -= cor;
        if (tid == 31) u.w -= cor;
        const uint32_t lo = pack2(v.x, v.y), hi = pack2(v.z, v.w);
        if (tid < 64) {
            E4[6 + tid] = make_uint2(lo, hi);
            E4[(tid < 32 ? 159 : 209 - 32) + tid] = make_uint2(pack2(u.x, u.y), pack2(u.z, u.w));
        } else {
            const uint32_t nx = __shfl_down_sync(~0u, lo, 1);
            in.tap[d * 128 + 35 + tid - 64] = make_uint4(__byte_perm(lo, 0, 0x1010), __byte_perm(lo, hi, 0x5432), __byte_perm(hi, 0, 0x1010), __byte_perm(hi, tid == 95 ? 0u : nx, 0x5432));
            if (tid == 64) E4[241] = make_uint2(pack2(u.x, 0.f), 0u);
        }
    }
    TSTAMPK(10, 64);
    if (warp < (blockIdx.x < 112 ? 2 : 1)) {
        const uint32_t sb = smem_u32(tabs);
        mbar_wait(sb + KG_BAR + 16 * warp, 0); mbar_wait(sb + KG_BAR + 16 * warp + 8, 0);
        uint32_t w[4][4];
        float cs[4] = {0.f, 0.f, 0.f, 0.f};
#pragma unroll
        for (int a = 0; a < 4; a++)
            ldsm_x4_t(w[a], sb + KG_BUF + warp * 10240 + grp * 1024 + ((lane >> 4) * 8 + (lane & 7)) * 32 + ((((lane >> 3) ^ (lane >> 2)) & 1) << 4) + (a >> 1) * 5120 + (a & 1) * 512);
#pragma unroll
        for (int a = 0; a < 4; a++) mma_bf16(cs, w[a][0], w[a][1], w[a][2], w[a][3], 0x3f803f80u, 0x3f803f80u);
        if (t < 2) in.csp[(blockIdx.x + 128 * warp) * 80 + grp * 16 + g + 8 * t] = t ? cs[2] : cs[0];
    }
    SPAN(0, 3);
}

#define CV_SLEEP 40
#define CV_D2 3
#define CV_PDH 12
#define CV_PDF 4
#define CV_HAND 7
constexpr int CV_CPB = 5;
constexpr int CV_THREADS = 512;
constexpr int UPADF = 128;
constexpr int ULEN = UPADF + SEQ;
constexpr int XLEN = SEQ + 16;
constexpr int BX_5 = 0, BX_3 = 3264, BX_9 = 6528, BX_7 = 8960, BX_LEN = 11392;
constexpr int CV_SM_U = 0;
constexpr int CV_SM_T = CV_CPB * ULEN * 2;
constexpr int CV_SM_B = CV_SM_T + CV_CPB * TAPB;
constexpr int CV_SM_X = CV_SM_B + CV_CPB * BX_LEN;
constexpr int CV_SM_Y = (CV_SM_X + CV_CPB * XLEN * 2 + 127) & ~127;
constexpr int CV_SM_CNT = CV_SM_Y + CV_CPB * 8192;
constexpr int CV_SM_O = CV_SM_CNT + 128;
constexpr int CV_SMEM = CV_SM_O + 20480 + CST_EXTRA;
static_assert(ULEN % 128 == 0 && CV_SM_B % 128 == 0 && CV_SM_CNT % 128 == 0, "layout");

__device__ __forceinline__ uint32_t sub2(uint32_t x, uint32_t m) {
    const __nv_bfloat162 d = __hsub2(*reinterpret_cast<const __nv_bfloat162*>(&x), *reinterpret_cast<const __nv_bfloat162*>(&m));
    return *reinterpret_cast<const uint32_t*>(&d);
}
__device__ __forceinline__ uint32_t add2(uint32_t x, uint32_t y) {
    const __nv_bfloat162 d = __hadd2_rn(*reinterpret_cast<const __nv_bfloat162*>(&x), *reinterpret_cast<const __nv_bfloat162*>(&y));
    return *reinterpret_cast<const uint32_t*>(&d);
}
__device__ __forceinline__ void wgmma_fence() { asm volatile("wgmma.fence.sync.aligned;" ::: "memory"); }
__device__ __forceinline__ void wgmma_commit() { asm volatile("wgmma.commit_group.sync.aligned;" ::: "memory"); }
template <int N> __device__ __forceinline__ void wgmma_wait() { asm volatile("wgmma.wait_group.sync.aligned %0;" ::"n"(N) : "memory"); }
__device__ __forceinline__ uint64_t make_desc(uint32_t addr, uint32_t lbo, uint32_t sbo, uint32_t mode) {
    return (uint64_t)((addr & 0x3FFFF) >> 4) | ((uint64_t)(lbo >> 4) << 16) | ((uint64_t)(sbo >> 4) << 32) | ((uint64_t)mode << 62);
}
__device__ __forceinline__ void wgmma_rs128(float (&d)[64], uint2 hi, uint2 lo, uint64_t db, int acc) {
    asm volatile("{\n.reg .pred p;\nsetp.ne.b32 p, %69, 0;\nwgmma.mma_async.sync.aligned.m64n128k16.f32.bf16.bf16 {%0,%1,%2,%3,%4,%5,%6,%7,%8,%9,%10,%11,%12,%13,%14,%15,%16,%17,%18,%19,%20,%21,%22,%23,%24,%25,%26,%27,%28,%29,%30,%31,%32,%33,%34,%35,%36,%37,%38,%39,%40,%41,%42,%43,%44,%45,%46,%47,%48,%49,%50,%51,%52,%53,%54,%55,%56,%57,%58,%59,%60,%61,%62,%63}, {%64,%65,%66,%67}, %68, p, 1, 1, 0;\n}"
                 : "+f"(d[0]), "+f"(d[1]), "+f"(d[2]), "+f"(d[3]), "+f"(d[4]), "+f"(d[5]), "+f"(d[6]), "+f"(d[7]), "+f"(d[8]), "+f"(d[9]), "+f"(d[10]), "+f"(d[11]), "+f"(d[12]), "+f"(d[13]), "+f"(d[14]), "+f"(d[15]), "+f"(d[16]), "+f"(d[17]), "+f"(d[18]), "+f"(d[19]), "+f"(d[20]), "+f"(d[21]), "+f"(d[22]), "+f"(d[23]), "+f"(d[24]), "+f"(d[25]), "+f"(d[26]), "+f"(d[27]), "+f"(d[28]), "+f"(d[29]), "+f"(d[30]), "+f"(d[31]), "+f"(d[32]), "+f"(d[33]), "+f"(d[34]), "+f"(d[35]), "+f"(d[36]), "+f"(d[37]), "+f"(d[38]), "+f"(d[39]), "+f"(d[40]), "+f"(d[41]), "+f"(d[42]), "+f"(d[43]), "+f"(d[44]), "+f"(d[45]), "+f"(d[46]), "+f"(d[47]), "+f"(d[48]), "+f"(d[49]), "+f"(d[50]), "+f"(d[51]), "+f"(d[52]), "+f"(d[53]), "+f"(d[54]), "+f"(d[55]), "+f"(d[56]), "+f"(d[57]), "+f"(d[58]), "+f"(d[59]), "+f"(d[60]), "+f"(d[61]), "+f"(d[62]), "+f"(d[63])
                 : "r"(hi.x), "r"(hi.y), "r"(lo.x), "r"(lo.y), "l"(db), "r"(acc));
}
template <int V> struct Int { __device__ constexpr operator int() const { return V; } };
__device__ __forceinline__ void sts4(uint32_t a, const uint32_t* v) { asm volatile("st.shared.v4.u32 [%0], {%1,%2,%3,%4};" ::"r"(a), "r"(v[0]), "r"(v[1]), "r"(v[2]), "r"(v[3]) : "memory"); }
__device__ __forceinline__ uint32_t lds1(uint32_t a) { uint32_t v; asm volatile("ld.shared.u32 %0, [%1];" : "=r"(v) : "r"(a) : "memory"); return v; }
__device__ __forceinline__ uint4 lds4(uint32_t a) { uint4 v; asm volatile("ld.shared.v4.u32 {%0,%1,%2,%3}, [%4];" : "=r"(v.x), "=r"(v.y), "=r"(v.z), "=r"(v.w) : "r"(a) : "memory"); return v; }
__device__ __forceinline__ void cv_store(unsigned char* p, uint4 x, uint4 y) {
    asm volatile("st.relaxed.gpu.global.v2.u32 [%0], {%1,%2};" ::"l"(p), "r"(add2(x.x, __byte_perm(y.x, y.y, 0x5410))), "r"(add2(x.y, __byte_perm(y.z, y.w, 0x5410))) : "memory");
    asm volatile("st.relaxed.gpu.global.v2.u32 [%0], {%1,%2};" ::"l"(p + 128), "r"(add2(x.z, __byte_perm(y.x, y.y, 0x7632))), "r"(add2(x.w, __byte_perm(y.z, y.w, 0x7632))) : "memory");
}
__device__ __forceinline__ int usw(int ch) { return ch ^ ((ch >> 3) & 1); }
__global__ void __launch_bounds__(CV_THREADS, 1) conv_kernel(int layer, const uint4* __restrict__ piv, const float4* __restrict__ sum, const bf16* __restrict__ x1T,
                                                             bf16* __restrict__ dst, const uint4* __restrict__ tap, const __grid_constant__ CUtensorMap tmOut) {
    extern __shared__ __align__(1024) unsigned char sm[];
    SPAN(3 + 4 * layer, 0);
    bf16* Us = reinterpret_cast<bf16*>(sm + CV_SM_U);
    bf16* Xs = reinterpret_cast<bf16*>(sm + CV_SM_X);
#define CV_IDX int tid; asm volatile("mov.u32 %0, %tid.x;" : "=r"(tid)); const int lane = tid & 31, warp = __shfl_sync(~0u, tid >> 5, 0);
    const int d0 = blockIdx.x * CV_CPB, tile = blockIdx.x; (void)tile;
    const uint32_t cnt = smem_u32(sm + CV_SM_CNT);
    struct Lc { uint32_t a4, a8, uc, ud, y, e4, en, sp, ss; int go; };
    auto lane_consts = [&](int lane, int c) {
        const int mat = lane >> 3, r = lane & 7, g = lane >> 2, ti = lane & 3, e = g - 2 * ti;
        const int j2 = 13 + (r ^ 1) + 8 * (mat >> 1), j3 = j2 + 2, i0 = 8 * (mat & 1);
        const uint32_t sb = smem_u32(sm), oc = sb + usw(16 * (mat >> 1) + 2 * r + (mat & 1)) * 16;
        const Lc l = {sb + CV_SM_B + c * BX_LEN + ((j2 & 1) ? BX_3 + (4 * j2 + i0 + 84) * 2 : BX_5 + (4 * j2 + i0 + 80) * 2),
                      sb + CV_SM_B + c * BX_LEN + ((j3 & 1) ? BX_7 : BX_9) + (8 * j3 + i0 + 136) * 2,
                      oc + CV_SM_U + (c * ULEN + UPADF) * 2, sb + CV_SM_U + (c * ULEN + UPADF) * 2 + usw(16 * mat + 2 * r + 2) * 16, oc + CV_SM_Y + c * 8192,
                      sb + CV_SM_O + 2048 * c + (307 + 2 * g - ti) * 4, sb + CV_SM_T + c * TAPB + (152 + 144 + e) * 8 + 4,
                      e == -5 ? 0x4410u : e == -4 ? 0x1044u : 0x4444u, e == 3 ? 0x4410u : e == 4 ? 0x1044u : 0x4444u,
                      c * XCP * 2 + (lane >> 4) * 256 + (lane & 15) * 8};
        asm volatile("st.shared.u32 [%0], %1;" ::"r"(l.y), "r"(l.a4 ^ l.a8 ^ l.uc ^ l.ud ^ l.e4 ^ l.en ^ l.sp ^ l.ss ^ l.go) : "memory");
        return l;
    };
    unsigned char* const dq = reinterpret_cast<unsigned char*>(dst + (size_t)d0 * XCP);
    auto far = [&](auto T0_, const auto& seq, const Lc& lc, int c, int lane, const uint2 (&f)[20], uint32_t kk) {
        constexpr int T0 = T0_, T1 = T0 + 6, TC = T0 > 7 ? T0 : 7, NS = sizeof(seq) / sizeof(seq[0]), PD = T0 > 7 ? CV_PDH : CV_PDF;
        uint32_t bq[28], yw[4], yz[4], P, S;
        uint4 xv, yv;
        asm("prmt.b32 %0, %1, 0, %2;" : "=r"(P) : "r"(kk), "r"(lc.sp));
        asm("prmt.b32 %0, %1, 0, %2;" : "=r"(S) : "r"(kk), "r"(lc.ss));
#pragma unroll
        for (int k = 0; 2 * k < T1 - TC + 4; k++) ldsm_x4(bq + 4 * k, lc.uc + (TC - 8) * 256 + 512 * k);
#pragma unroll
        for (int k = 0; 4 * k < T1 - TC; k++) ldsm_x4(bq + 20 + 4 * k, lc.ud + (TC - 8) * 256 + 1024 * k);
        CST(3);
        mbar_wait(cnt + 8 * c, 0);
        mbar_wait(cnt + 40, 0);
        CST(4);
        float acc[6][4] = {};
        uint32_t a[PD + 1][4];
#pragma unroll
        for (int i = -PD; i < NS + 3; i++) {
            if (i + PD < NS) ldsm_x4_t(a[(i + PD) % (PD + 1)], seq[i + PD] < 32 ? lc.a4 + (seq[i + PD] - 2) * 128 : lc.a8 + (seq[i + PD] - 34) * 256);
            if (i < 0) continue;
#pragma unroll
            for (int T = T0; T < T1; T++) {
                if (i >= NS) break;
                const int ee = seq[i] < 32 ? 2 * T - 6 - seq[i] : T + 35 - seq[i];
                if (i == 0 && T >= TC) mma_bf16(acc[T - T0], P, 0u, S, P, bq[2 * (T - TC)], bq[2 * (T - TC) + 1]);
                if (i == 1 && T >= TC) mma_bf16_k8(acc[T - T0], 0u, S, bq[20 + T - TC]);
                if (i == (T >= TC ? 2 : 0)) mma_bf16(acc[T - T0], f[19].x, 0u, f[19].y, f[19].x, bq[2 * (T - TC + 4)], bq[2 * (T - TC + 4) + 1]);
                if (seq[i] < 32 ? ee >= 0 && ee <= 9 : ee >= 10) mma_bf16(acc[T - T0], a[i % (PD + 1)][0], a[i % (PD + 1)][1], a[i % (PD + 1)][2], a[i % (PD + 1)][3], f[ee].x, f[ee].y);
            }
#pragma unroll
            for (int k = 0; k < 3; k++) {
                const int o = 256 * T0 + 512 * k;
                auto at = [&](int d) { return i - d >= 0 && i - d < NS && seq[i - d < 0 ? 0 : i - d < NS ? i - d : 0] == 2 * T0 + 4 * k - 4; };
                if (at(CV_D2)) {
                    cv_store(dq + lc.go + o, xv, yv);
                    if (layer > 19 - 2 * k) __trap();
                }
                if (at(-2)) { ldsm_x4_t(yw, lc.y + o); ldsm_x4_t(yz, lc.y + 3584 + o); }
                if (at(1)) {
#pragma unroll
                    for (int q = 0; q < 4; q++) yw[q] = add2(add2(yw[q], yz[q]), pack2(acc[2 * k + (q >> 1)][2 * (q & 1)], acc[2 * k + (q >> 1)][2 * (q & 1) + 1]));
                    stsm_x4_t(lc.y + o, yw[0], yw[1], yw[2], yw[3]);
                    xv = lds4(smem_u32(Xs + c * XLEN) + o + lane * 16);
                    __syncwarp();
                    yv = lds4(smem_u32(sm + CV_SM_Y) + c * 8192 + o + usw(lane) * 16);
                    if (layer > 20 - 2 * k) __trap();
                    if (k == 2) CST(6);
                }
            }
        }
    };
    TSTAMP1X(9, 256);
    if (threadIdx.x >= 256) {
        CV_IDX
        const int t2 = tid - 256, wgu = (warp >> 2) & 1, g = lane >> 2, ti = lane & 3;
        if (t2 == 0) {
            mbar_init(cnt + 48, 1);
            asm volatile("fence.mbarrier_init.release.cluster;" ::: "memory");
            mbar_expect_tx(cnt + 48, CV_CPB * 2048);
            bulk_load(smem_u32(sm + CV_SM_O), tap + d0 * 128, CV_CPB * 2048, cnt + 48);
        } else if (lane == 0) {
            if (warp < 15) mbar_init(cnt + 8 * (warp - 9), warp == 14 ? 8 : 4);
            else if (layer) prefetch_tmap(&tmOut);
        }
        if (t2 < 140) {
            const int k = t2;
            const int off = k < 20 ? CV_SM_B + BX_5 + 8 * k : k < 40 ? CV_SM_B + BX_3 + 8 * (k - 20) : k < 74 ? CV_SM_B + BX_9 + 8 * (k - 40) : k < 108 ? CV_SM_B + BX_7 + 8 * (k - 74) : CV_SM_U + 8 * (k - 108);
            const int str = k < 108 ? BX_LEN : ULEN * 2;
#pragma unroll
            for (int c = 0; c < CV_CPB; c++) *reinterpret_cast<uint2*>(sm + off + c * str) = make_uint2(0, 0);
        }
        fence_async_smem();
        asm volatile("bar.arrive 3, 512;" ::: "memory");
        asm volatile("bar.sync 1, 256;" ::: "memory");
        TSTAMP1X(10, 256);
        asm volatile("setmaxnreg.inc.sync.aligned.u32 168;");
        const int hc = wgu ? warp & 3 : 4;
        const Lc lc = lane_consts(lane, hc);
        const uint32_t* E2[3];
#pragma unroll
        for (int k = 0; k < 3; k++) {
            const int i = min(t2 + 256 * k, 759), h = i / 76;
            E2[k] = reinterpret_cast<const uint32_t*>(sm + CV_SM_O) + 3 + i + (h >> 1) * 360 + (h & 1) * 52;
        }
        mbar_wait(cnt + 48, 0);
        TSTAMP1X(11, 256);
        {
            uint32_t w[3][4];
#pragma unroll
            for (int k = 0; k < 3; k++) { w[k][0] = E2[k][0]; w[k][1] = E2[k][1]; w[k][2] = E2[k][64]; w[k][3] = E2[k][65]; }
#pragma unroll
            for (int k = 0; k < 3; k++)
                *reinterpret_cast<uint4*>(sm + CV_SM_T + min(t2 + 256 * k, 759) * 16) =
                    make_uint4(__byte_perm(w[k][1], w[k][0], 0x7610), __byte_perm(w[k][3], w[k][2], 0x7610), __byte_perm(w[k][1], 0, 0x1032), __byte_perm(w[k][3], 0, 0x1032));
        }
        asm volatile("bar.sync 1, 256;" ::: "memory");
        const uint2* Tc = reinterpret_cast<const uint2*>(sm + CV_SM_T) + 16 + 76 * (warp & 2) + 8 * (warp & 1) + g - 2 * ti;
        uint2 fa[8][2], fn[8][2];
        auto near_taps = [&](uint2 (&f)[8][2], int c) {
#pragma unroll
            for (int m = 0; m < 8; m++) { f[m][0] = Tc[c * (TAPB / 8) + 16 * m]; f[m][1] = Tc[c * (TAPB / 8) + 16 * m - 8]; }
        };
        near_taps(fa, 3 * wgu);
        near_taps(fn, 2 - wgu);
        TSTAMP1X(12, 256); CST(0);
        uint32_t ya = smem_u32(sm + CV_SM_Y) + wgu * 8192 + (warp & 2) * 2048 + usw(2 * lane + (warp & 1)) * 16;
        uint64_t db = make_desc(smem_u32(Us + wgu * ULEN + UPADF), 16, 256, 3);
        if (wgu) asm volatile("bar.sync 6, 384;" ::: "memory");
        int c = wgu;
        auto chain = [&](const uint2 (&f)[8][2], auto&& meanwhile) {
            float acc[64];
            asm volatile("bar.sync %0, %1;" ::"r"(c ? 4 + wgu : 2), "r"(c ? 256 : 384) : "memory");
            TSTAMPC(1 + 3 * c);
            wgmma_fence();
#pragma unroll
            for (int m = 0; m < 8; m++) {
                wgmma_rs128(acc, f[m][0], f[m][1], db - (uint64_t)(2 * m), m);
                if (m == CV_HAND && c < 4) asm volatile("bar.arrive %0, 256;" ::"r"(5 - wgu) : "memory");
            }
            wgmma_commit();
            asm volatile("griddepcontrol.launch_dependents;" ::: "memory");
            TSTAMPC(2 + 3 * c); CST(13 + (c >> 1));
            meanwhile();
            wgmma_wait<0>();
            TSTAMPC(3 + 3 * c); CST(10 + (c >> 1));
            uint32_t w[16];
#pragma unroll
            for (int j = 0; j < 16; j++) w[j] = j ? pack2(acc[4 * j] + acc[4 * j - 2], acc[4 * j + 1] + acc[4 * j - 1]) : pack2(acc[0], acc[1]);
#pragma unroll
            for (int j = 0; j < 16; j += 4) stsm_x4_t(ya + 256 * j, w[j], w[j + 1], w[j + 2], w[j + 3]);
            __syncwarp();
            if (lane == 0) mbar_arrive(cnt + 8 * c);
            c += 2; ya += 16384; db += ULEN / 4;
        };
        const uint32_t e4 = lc.e4, e8 = e4 + 428 - 4 * g;
        uint2 fl[4];
        uint32_t kk;
#pragma unroll 1
        for (;;) {
            if (c != 1) chain(fa, [&] {
                if (c == 3 || warp + c == 12) {
#pragma unroll
                    for (int k = 0; k < 19; k++) (k < 16 ? fn[(k >> 1) & 7][k & 1] : fl[k & 3]) = make_uint2(lds1(k < 10 ? e4 + 32 * k + 16 : e8 + 32 * k - 304), lds1(k < 10 ? e4 + 32 * k : e8 + 32 * k - 320));
                    fl[3] = make_uint2(lds1(lc.en), lds1(lc.en - 64));
                    kk = lds1(smem_u32(sm + CV_SM_O) + 2048 * hc + 1672);
                }
            });
            if (c > 4) break;
            if (c == 2) asm volatile("bar.sync 7, 384;" ::: "memory");
            chain(fn, [&] { if (c == 2) near_taps(fa, 4); });
        }
        TSTAMP1X(6, 256); CST(2);
        if (wgu || warp == 8) {
            constexpr int seq[29] = {5, 6, 32, 7, 33, 8, 34, 9, 35, 10, 36, 11, 12, 13, 14, 15, 16, 17, 37, 18, 38, 19, 20, 21, 39, 22, 40, 23, 24};
            uint2 f[20];
#pragma unroll
            for (int k = 0; k < 20; k++) f[k] = k < 16 ? fn[(k >> 1) & 7][k & 1] : fl[k & 3];
            far(Int<10>(), seq, lc, hc, lane, f, kk);
        }
    } else {
        asm volatile("setmaxnreg.dec.sync.aligned.u32 88;");
        CV_IDX
        const uint4* ppv = piv + tid;
        const float4* psv = sum + tid;
        const uint2* pxv = reinterpret_cast<const uint2*>(x1T + (size_t)d0 * XCP) + (tid >> 4) * 32 + (tid & 15);
        asm volatile("st.shared.u64 [%0], %1;" ::"r"(smem_u32(Xs) + tid * 16), "l"((uint64_t)ppv ^ (uint64_t)psv ^ (uint64_t)pxv) : "memory");
        const int tc = (0x04302100 >> (4 * warp)) & 7;
        const Lc lc = lane_consts(lane, tc);
        pdl_sync();
        SPAN(3 + 4 * layer, 1);
        TSTAMP(0); CST(0);
        if (tid == 0) TSTAMPC(0);
        if (threadIdx.x == 0) { GSTAMP(g_tim, 15); }
        float4 sv[4];
#pragma unroll
        for (int k = 0; k < 4; k++)
            asm volatile("ld.relaxed.gpu.global.v4.f32 {%0,%1,%2,%3}, [%4];" : "=f"(sv[k].x), "=f"(sv[k].y), "=f"(sv[k].z), "=f"(sv[k].w) : "l"(psv + 256 * k) : "memory");
        uint4 pv;
        asm volatile("ld.relaxed.gpu.global.v4.u32 {%0,%1,%2,%3}, [%4];" : "=r"(pv.x), "=r"(pv.y), "=r"(pv.z), "=r"(pv.w) : "l"(ppv) : "memory");
        uint2 xe[CV_CPB], xo[CV_CPB];
#pragma unroll
        for (int c = 0; c < CV_CPB; c++) {
            asm volatile("ld.relaxed.gpu.global.v2.u32 {%0,%1}, [%2];" : "=r"(xe[c].x), "=r"(xe[c].y) : "l"(pxv + c * (XCP / 4)) : "memory");
            asm volatile("ld.relaxed.gpu.global.v2.u32 {%0,%1}, [%2];" : "=r"(xo[c].x), "=r"(xo[c].y) : "l"(pxv + c * (XCP / 4) + 16) : "memory");
        }
        constexpr float idm = 1.0f / DM;
        uint32_t mw[4];
        float rs[8];
#pragma unroll
        for (int k = 0; k < 4; k++) {
            const uint32_t pw = k == 0 ? pv.x : k == 1 ? pv.y : k == 2 ? pv.z : pv.w;
            const float d0_ = sv[k].x * idm, d1_ = sv[k].z * idm;
            mw[k] = pack2(__uint_as_float(pw << 16) + d0_, __uint_as_float(pw & 0xffff0000u) + d1_);
            const uint32_t vr = pack2(fmaxf(fmaf(-d0_, d0_, sv[k].y * idm), 0.f), fmaxf(fmaf(-d1_, d1_, sv[k].w * idm), 0.f));
            const uint32_t ve = pack2(__uint_as_float(vr << 16) + 1e-5f, __uint_as_float(vr & 0xffff0000u) + 1e-5f);
            const uint32_t sd = pack2(sqrt_apx(__uint_as_float(ve << 16)), sqrt_apx(__uint_as_float(ve & 0xffff0000u)));
            rs[2 * k] = rcp_apx(__uint_as_float(sd << 16)); rs[2 * k + 1] = rcp_apx(__uint_as_float(sd & 0xffff0000u));
        }
        if (rs[0] != 123.f) TSTAMP(13);
        const uint32_t ua = smem_u32(Us) + usw(tid + UPADF / 8) * 16;
        uint32_t uw[CV_CPB][4];
#pragma unroll
        for (int c = 0; c < CV_CPB; c++) {
            const uint32_t e0 = sub2(xe[c].x, mw[0]), e1 = sub2(xe[c].y, mw[1]), o0 = sub2(xo[c].x, mw[2]), o1 = sub2(xo[c].y, mw[3]);
            uw[c][0] = pack2(__uint_as_float(e0 << 16) * rs[0], __uint_as_float(o0 << 16) * rs[4]); uw[c][1] = pack2(__uint_as_float(e0 & 0xffff0000u) * rs[1], __uint_as_float(o0 & 0xffff0000u) * rs[5]);
            uw[c][2] = pack2(__uint_as_float(e1 << 16) * rs[2], __uint_as_float(o1 << 16) * rs[6]); uw[c][3] = pack2(__uint_as_float(e1 & 0xffff0000u) * rs[3], __uint_as_float(o1 & 0xffff0000u) * rs[7]);
            asm volatile("st.shared.v4.u32 [%0], {%1,%2,%3,%4};" ::"r"(ua + c * ULEN * 2), "r"(uw[c][0]), "r"(uw[c][1]), "r"(uw[c][2]), "r"(uw[c][3]) : "memory");
            if (c < 2) {
                fence_async_smem();
                asm volatile("bar.arrive %0, 384;" ::"r"(2 + 4 * c) : "memory");
                if (layer > 29 - c) __trap();
            }
        }
        fence_async_smem();
#pragma unroll
        for (int c = 0; c < CV_CPB; c++) *reinterpret_cast<uint4*>(Xs + c * XLEN + tid * 8) = make_uint4(xe[c].x, xe[c].y, xo[c].x, xo[c].y);
        asm volatile("bar.arrive 7, 384;" ::: "memory");
        asm volatile("bar.sync 3, 512;" ::: "memory");
        TSTAMP(1); CST(1);
        {
            auto box = [&](auto c0, auto c1, int chunk, int cb, bool full) {
                const uint32_t ea = smem_u32(Us + cb * ULEN) + usw(chunk + UPADF / 8 + (lane ? 1 : -1)) * 16, bx = smem_u32(sm + CV_SM_B + cb * BX_LEN) + chunk * 16;
                uint32_t lo[CV_CPB][4], hi[CV_CPB][2];
#pragma unroll
                for (int c = c0; c < c1; c++) {
                    lo[c][0] = 0;
#pragma unroll
                    for (int k = 1; k < 4; k++) lo[c][k] = __shfl_up_sync(~0u, uw[c][k], 1);
#pragma unroll
                    for (int k = 0; k < 2; k++) hi[c][k] = __shfl_down_sync(~0u, uw[c][k], 1);
                }
#pragma unroll
                for (int c = c0; c < c1; c++)
                    asm volatile("{\n.reg .pred p, q;\nsetp.eq.s32 p, %7, 0;\nsetp.eq.s32 q, %7, 31;\n@p ld.shared.v4.u32 {%0,%1,%2,%3}, [%6];\n@q ld.shared.v2.u32 {%4,%5}, [%6];\n}"
                                 : "+r"(lo[c][0]), "+r"(lo[c][1]), "+r"(lo[c][2]), "+r"(lo[c][3]), "+r"(hi[c][0]), "+r"(hi[c][1]) : "r"(ea + c * ULEN * 2), "r"(lane) : "memory");
#pragma unroll
                for (int c = c0; c < c1; c++) {
                    const uint32_t e[9] = {lo[c][1], lo[c][2], lo[c][3], uw[c][0], uw[c][1], uw[c][2], uw[c][3], hi[c][0], hi[c][1]};
                    uint32_t o[8], p[8], t[7], b3[5], b5[7];
#pragma unroll
                    for (int i = 0; i < 8; i++) { o[i] = __byte_perm(e[i], e[i + 1], 0x5432); p[i] = add2(e[i], o[i]); }
#pragma unroll
                    for (int i = 0; i < 5; i++) b3[i] = add2(o[i], p[i + 1]);
                    sts4(bx + c * BX_LEN + BX_3 + 160, b3);
#pragma unroll
                    for (int i = 1; i < 7; i++) { t[i] = add2(p[i], p[i + 1]); b5[i] = add2(t[i], e[i + 2]); }
                    sts4(bx + c * BX_LEN + BX_5 + 160, b5 + 2);
                    if (full) {
#pragma unroll
                        for (int i = 1; i < 5; i++) { b3[i] = add2(b3[i], t[i + 2]); t[i] = add2(t[i], b5[i + 2]); }
                        sts4(bx + c * BX_LEN + BX_7 + 272, b3 + 1);
                        sts4(bx + c * BX_LEN + BX_9 + 272, t + 1);
                    }
                }
            };
            auto reload = [&](int c, uint32_t a) { const uint4 v = lds4(a); uw[c][0] = v.x; uw[c][1] = v.y; uw[c][2] = v.z; uw[c][3] = v.w; };
            if (warp >= 6) {
#pragma unroll
                for (int c = 0; c < 3; c++) reload(c, ua - 1024 + (c + 2) * ULEN * 2);
            }
            if (warp >= 4) {
#pragma unroll
                for (int c = 3; c < 5; c++) reload(c, ua - 2048 + c * ULEN * 2);
            }
            box(Int<0>(), Int<3>(), warp < 6 ? tid : tid - 64, warp < 6 ? 0 : 2, warp < 4);
            if (warp >= 4) box(Int<3>(), Int<5>(), tid - 128, 0, true);
            else if (tid >= 128 - CV_CPB) {
                const int c = 127 - tid;
                const uint2 v = *reinterpret_cast<const uint2*>(Us + c * ULEN + UPADF);
                const float s1 = __uint_as_float(v.x << 16), s2 = s1 + __uint_as_float(v.x & 0xffff0000u), s3 = s2 + __uint_as_float(v.y << 16), s4 = s3 + __uint_as_float(v.y & 0xffff0000u);
                unsigned char* bc = sm + CV_SM_B + c * BX_LEN;
                *reinterpret_cast<uint32_t*>(bc + BX_5 + 156) = pack2(s1, s2);
                *reinterpret_cast<uint2*>(bc + BX_7 + 264) = make_uint2(v.x << 16, pack2(s2, s3));
                *reinterpret_cast<uint2*>(bc + BX_9 + 264) = make_uint2(pack2(s1, s2), pack2(s3, s4));
            }
        }
        __syncwarp();
        if (lane == 0) mbar_arrive(cnt + 40);
        TSTAMP(2); CST(2);
        if (layer && blockIdx.x == 0 && tid == 224) g_epoch = ld_epoch();
        __syncwarp();
        if ((0x6e >> warp) & 1) {
            constexpr int seq[16] = {0, 1, 2, 3, 4, 5, 6, 32, 7, 8, 9, 33, 10, 34, 11, 12};
            uint2 f[20];
            mbar_wait(cnt, 0);
            const uint32_t e8 = lc.e4 + 428 - (lane & 28);
#pragma unroll
            for (int k = 0; k < 13; k++) f[k] = make_uint2(lds1(k < 10 ? lc.e4 + 32 * k + 16 : e8 + 32 * k - 304), lds1(k < 10 ? lc.e4 + 32 * k : e8 + 32 * k - 320));
            f[19] = make_uint2(lds1(lc.en), lds1(lc.en - 64));
            far(Int<4>(), seq, lc, tc, lane, f, lds1(smem_u32(sm + CV_SM_O) + 2048 * tc + 1672));
        }
    }
    {
        CV_IDX
        if ((0xc91 >> warp) & 1) {
            const int c = __popc(0xc91 & ((1 << warp) - 1));
            uint4 xv[2], yv[2];
#pragma unroll
            for (int k = 0; k < 2; k++) xv[k] = lds4(smem_u32(Xs + c * XLEN) + 512 * k + lane * 16);
            const uint32_t u0 = lds1(smem_u32(Us + c * ULEN) + (lane == 31 ? UPADF * 2 : 0));
            mbar_wait(cnt + 8 * c, 0);
#pragma unroll
            for (int k = 0; k < 2; k++) yv[k] = lds4(smem_u32(sm + CV_SM_Y) + c * 8192 + 512 * k + usw(lane) * 16);
            const uint4 yz = lds4(smem_u32(sm + CV_SM_Y) + c * 8192 + 4096 + usw(lane) * 16);
            const float kk = __uint_as_float(lds1(smem_u32(sm + CV_SM_O) + 2048 * c + 1272) << 16);
            yv[1].x = add2(yv[1].x, yz.x); yv[1].y = add2(yv[1].y, yz.y); yv[1].z = add2(yv[1].z, yz.z);
            yv[1].w = pack2(fmaf(kk, __uint_as_float(u0 << 16), __uint_as_float(yv[1].w << 16) + __uint_as_float(yz.w << 16)),
                            fmaf(kk, __uint_as_float(u0 << 16) + __uint_as_float(u0 & 0xffff0000u), __uint_as_float(yv[1].w & 0xffff0000u) + __uint_as_float(yz.w & 0xffff0000u)));
#pragma unroll
            for (int k = 0; k < 2; k++) cv_store(dq + c * XCP * 2 + (lane >> 4) * 256 + (lane & 15) * 8 + 512 * k, xv[k], yv[k]);
        }
        TSTAMP(4); CST(8);
        if (layer == 1) {
            const int rb = (blockIdx.x >> 3) + (warp & 8) * 2, cg = blockIdx.x & 7, ch = (tid >> 3) & 31;
            const bf16* src = dst + (size_t)(cg * 80 + ch) * XCP + rb * 64 + (tid & 7) * 8;
            uint32_t v[3][4];
            __syncthreads();
            if (warp & 8) { const uint32_t c0 = clock(); while (clock() - c0 < 300) ; }
            uint32_t todo = (warp & 4) ? 3 : 7;
#pragma unroll 1
            for (int it = 0; it < SPIN_MAX; it++) {
#pragma unroll
                for (int k = 0; k < 3; k++)
                    if (todo >> k & 1)
                        asm volatile("ld.relaxed.gpu.global.v4.u32 {%0,%1,%2,%3}, [%4];" : "=r"(v[k][0]), "=r"(v[k][1]), "=r"(v[k][2]), "=r"(v[k][3]) : "l"(src + k * (32 * XCP)) : "memory");
#pragma unroll
                for (int k = 0; k < 3; k++)
                    if ((todo >> k & 1) && v[k][0] != ~0u && v[k][1] != ~0u && v[k][2] != ~0u && v[k][3] != ~0u) {
                        *reinterpret_cast<uint4*>(sm + (32 * k + ch) * 272 + ((tid & 7) + (warp & 8)) * 16) = make_uint4(v[k][0], v[k][1], v[k][2], v[k][3]);
                        todo ^= 1u << k;
                    }
                if (!todo) break;
                __nanosleep(CV_SLEEP);
            }
            __syncwarp();
            asm volatile("bar.sync %0, 256;" ::"r"(8 + (warp >> 3)) : "memory");
            uint32_t w[12];
#pragma unroll
            for (int k = 0; k < 3; k++) ldsm_x4(&w[4 * k], smem_u32(sm) + min(32 * k + lane, 79) * 272 + warp * 16);
            const uint32_t ot = smem_u32(sm + CV_SM_O) + warp * 1280, oa = ot + (lane & 7) * 160 + (lane >> 3) * 16;
            stsm_x4_t(oa, w[0], w[1], w[2], w[3]);
            stsm_x4_t(oa + 64, w[4], w[5], w[6], w[7]);
            asm volatile("stmatrix.sync.aligned.m8n8.x2.trans.shared.b16 [%0], {%1,%2};" ::"r"(oa + 128), "r"(w[8]), "r"(w[9]) : "memory");
            fence_async_smem();
            __syncwarp();
            if (lane == 0) {
                asm volatile("cp.async.bulk.tensor.3d.global.shared::cta.bulk_group [%0, {%1, %2, %3}], [%4];" ::"l"(&tmOut), "r"(cg * 80), "r"((rb >> 1) * 64 + 8 * (warp & 7)), "r"(rb & 1), "r"(ot) : "memory");
                asm volatile("cp.async.bulk.commit_group;" ::: "memory");
                asm volatile("cp.async.bulk.wait_group.read 0;" ::: "memory");
            }
        }
    }
    TSTAMP(3); CST(9); CST_END;
    GSTAMP(g_tim, 14);
    SPAN(3 + 4 * layer, 3);
}

template <int TA, int TB>
__device__ __forceinline__ void wgmma_n240(float (&d)[120], uint64_t da, uint64_t db, int acc) {
    asm volatile("{\n.reg .pred p;\nsetp.ne.b32 p, %124, 0;\nwgmma.mma_async.sync.aligned.m64n240k16.f32.bf16.bf16 {%0,%1,%2,%3,%4,%5,%6,%7,%8,%9,%10,%11,%12,%13,%14,%15,%16,%17,%18,%19,%20,%21,%22,%23,%24,%25,%26,%27,%28,%29,%30,%31,%32,%33,%34,%35,%36,%37,%38,%39,%40,%41,%42,%43,%44,%45,%46,%47,%48,%49,%50,%51,%52,%53,%54,%55,%56,%57,%58,%59,%60,%61,%62,%63,%64,%65,%66,%67,%68,%69,%70,%71,%72,%73,%74,%75,%76,%77,%78,%79,%80,%81,%82,%83,%84,%85,%86,%87,%88,%89,%90,%91,%92,%93,%94,%95,%96,%97,%98,%99,%100,%101,%102,%103,%104,%105,%106,%107,%108,%109,%110,%111,%112,%113,%114,%115,%116,%117,%118,%119}, %120, %121, p, 1, 1, %122, %123;\n}"
                 : "+f"(d[0]), "+f"(d[1]), "+f"(d[2]), "+f"(d[3]), "+f"(d[4]), "+f"(d[5]), "+f"(d[6]), "+f"(d[7]), "+f"(d[8]), "+f"(d[9]), "+f"(d[10]), "+f"(d[11]), "+f"(d[12]), "+f"(d[13]), "+f"(d[14]), "+f"(d[15]), "+f"(d[16]), "+f"(d[17]), "+f"(d[18]), "+f"(d[19]), "+f"(d[20]), "+f"(d[21]), "+f"(d[22]), "+f"(d[23]), "+f"(d[24]), "+f"(d[25]), "+f"(d[26]), "+f"(d[27]), "+f"(d[28]), "+f"(d[29]), "+f"(d[30]), "+f"(d[31]), "+f"(d[32]), "+f"(d[33]), "+f"(d[34]), "+f"(d[35]), "+f"(d[36]), "+f"(d[37]), "+f"(d[38]), "+f"(d[39]), "+f"(d[40]), "+f"(d[41]), "+f"(d[42]), "+f"(d[43]), "+f"(d[44]), "+f"(d[45]), "+f"(d[46]), "+f"(d[47]), "+f"(d[48]), "+f"(d[49]), "+f"(d[50]), "+f"(d[51]), "+f"(d[52]), "+f"(d[53]), "+f"(d[54]), "+f"(d[55]), "+f"(d[56]), "+f"(d[57]), "+f"(d[58]), "+f"(d[59]), "+f"(d[60]), "+f"(d[61]), "+f"(d[62]), "+f"(d[63]), "+f"(d[64]), "+f"(d[65]), "+f"(d[66]), "+f"(d[67]), "+f"(d[68]), "+f"(d[69]), "+f"(d[70]), "+f"(d[71]), "+f"(d[72]), "+f"(d[73]), "+f"(d[74]), "+f"(d[75]), "+f"(d[76]), "+f"(d[77]), "+f"(d[78]), "+f"(d[79]), "+f"(d[80]), "+f"(d[81]), "+f"(d[82]), "+f"(d[83]), "+f"(d[84]), "+f"(d[85]), "+f"(d[86]), "+f"(d[87]), "+f"(d[88]), "+f"(d[89]), "+f"(d[90]), "+f"(d[91]), "+f"(d[92]), "+f"(d[93]), "+f"(d[94]), "+f"(d[95]), "+f"(d[96]), "+f"(d[97]), "+f"(d[98]), "+f"(d[99]), "+f"(d[100]), "+f"(d[101]), "+f"(d[102]), "+f"(d[103]), "+f"(d[104]), "+f"(d[105]), "+f"(d[106]), "+f"(d[107]), "+f"(d[108]), "+f"(d[109]), "+f"(d[110]), "+f"(d[111]), "+f"(d[112]), "+f"(d[113]), "+f"(d[114]), "+f"(d[115]), "+f"(d[116]), "+f"(d[117]), "+f"(d[118]), "+f"(d[119])
                 : "l"(da), "l"(db), "n"(TA), "n"(TB), "r"(acc));
}

__device__ __forceinline__ void wgmma_n80(float (&d)[40], uint64_t da, uint64_t db, int acc) {
    asm volatile("{\n.reg .pred p;\nsetp.ne.b32 p, %42, 0;\nwgmma.mma_async.sync.aligned.m64n80k16.f32.bf16.bf16 {%0,%1,%2,%3,%4,%5,%6,%7,%8,%9,%10,%11,%12,%13,%14,%15,%16,%17,%18,%19,%20,%21,%22,%23,%24,%25,%26,%27,%28,%29,%30,%31,%32,%33,%34,%35,%36,%37,%38,%39}, %40, %41, p, 1, 1, 0, 1;\n}"
                 : "+f"(d[0]), "+f"(d[1]), "+f"(d[2]), "+f"(d[3]), "+f"(d[4]), "+f"(d[5]), "+f"(d[6]), "+f"(d[7]), "+f"(d[8]), "+f"(d[9]), "+f"(d[10]), "+f"(d[11]), "+f"(d[12]), "+f"(d[13]), "+f"(d[14]), "+f"(d[15]), "+f"(d[16]), "+f"(d[17]), "+f"(d[18]), "+f"(d[19]), "+f"(d[20]), "+f"(d[21]), "+f"(d[22]), "+f"(d[23]), "+f"(d[24]), "+f"(d[25]), "+f"(d[26]), "+f"(d[27]), "+f"(d[28]), "+f"(d[29]), "+f"(d[30]), "+f"(d[31]), "+f"(d[32]), "+f"(d[33]), "+f"(d[34]), "+f"(d[35]), "+f"(d[36]), "+f"(d[37]), "+f"(d[38]), "+f"(d[39])
                 : "l"(da), "l"(db), "r"(acc));
}

constexpr int A1_THREADS = 384;
constexpr int A1_NST = 4;
#define A1_SKEW 8
constexpr int A1_STAGE = 16384 + WQ_STAGE;
constexpr int A1_KVP = 336;
constexpr int A1_SM_KV = 2 * A1_STAGE;
constexpr int A1_SM_BAR = A1_NST * A1_STAGE;
constexpr int A1_SM_RS = A1_SM_BAR + 512;
constexpr int A1_SM_W0 = A1_SM_BAR + 3072, A1_SM_W3 = A1_SM_BAR - 3 * WOB, A1_SM_A1 = 2 * WOB, A1_SM_A0 = A1_SM_A1 + 61440;
constexpr int A1_SM_XA = A1_SM_W0 + 2 * WOB, A1_SM_XB = A1_SM_XA + 2048;
constexpr int A1_SMEM = A1_SM_W0 + 3 * WOB + CST_EXTRA;
static_assert(A1_SM_W3 >= A1_SM_KV + 144 * A1_KVP && A1_SM_W3 % 512 == 0 && A1_SM_A1 % 1024 == 0 && A1_SM_A0 <= A1_SM_KV && A1_SM_A0 + 61440 <= A1_SM_W3 && A1_SMEM <= 232448, "layout");
__device__ __forceinline__ constexpr uint32_t wo_off(int h) { return h * WOB + (h < 3 ? A1_SM_W0 : h < 6 ? A1_SM_W3 - 3 * WOB : -6 * WOB); }
#define A1_FRED "red.relaxed.gpu.global.add.u32"
#define A1_FLD "ld.acquire.gpu.global.u32"
#define ST_SLEEP 20
#define ST_SLEEP0 300
#define WO_LATE bar_done
#define A1_P0 2
#define A1_PW (kb - 2)
#define A1_FSPIN SPIN_MAX
#define A1_FSLEEP 40
#define YT_LAYER 1
#define WOT 352
#define A1_WOAT 6

template <int L>
__device__ __forceinline__ void a1_mainloop(float (&acc)[120], uint32_t sbase, uint32_t bars, int wg, int tile) {
    constexpr int layer = L; (void)layer;
    const uint64_t da0 = L ? make_desc(sbase + wg * 8192, 8192, 1024, 1) : make_desc(sbase + wg * 8192, 16, 1024, 1), db0 = make_desc(sbase + 16384, 1024, 256, 3);
#pragma unroll 1
    for (int t = 0;; t++) {
        const int st = t % A1_NST;
        mbar_wait(bars + 8 * st, (t / A1_NST) & 1);
        if (t == A1_SKEW && wg == 0) mbar_wait(bars + 160, 0);
        TSTAMP3(1 + t);
        if (t == 0) CSA(0);
        wgmma_fence();
#pragma unroll
        for (int kk = 0; kk < 4; kk++) wgmma_n240<L, 1>(acc, da0 + (uint32_t)(st * (A1_STAGE / 16) + kk * (L ? 128 : 2)), db0 + (uint32_t)(st * (A1_STAGE / 16) + (kk >> 1) * (WQ_STAGE / 32) + (kk & 1) * 32), kk ? 1 : t);
        wgmma_commit();
        if (t == 9) break;
        if (t == A1_SKEW - 1 && wg == 0) wgmma_wait<0>(); else wgmma_wait<1>();
        if (t > 0 && (threadIdx.x & 127) == 0) {
            if (t != A1_SKEW || wg) mbar_arrive(bars + 8 * (A1_NST + (t - 1) % A1_NST));
            if (t == A1_SKEW - 1 && wg == 0) mbar_arrive(bars + 8 * (A1_NST + t % A1_NST));
        }
    }
}

template <bool MAP>
__global__ void __launch_bounds__(A1_THREADS, 1) a1_kernel(const int layer, const bf16* __restrict__ x0, const unsigned char* __restrict__ wo,
                                                           float2* __restrict__ rsum, uint4* __restrict__ of, const __grid_constant__ CUtensorMap tmX,
                                                           const __grid_constant__ CUtensorMap tmR, const __grid_constant__ CUtensorMap tmX1, const __grid_constant__ TileTab tab) {
    extern __shared__ __align__(1024) unsigned char stg[];
    const uint32_t sbase = smem_u32(stg);
    const uint32_t bars = sbase + A1_SM_BAR;
    const uint32_t bar_stat = bars + 64, bar_kv = bars + 72, bar_rd = bars + 168;
    const uint32_t bar_wo = bars + 208, bar_done = bars + 216, bar_pv = bars + 224, bar_kvf = bars + 232, bar_f2 = bars + 248, bar_e2 = bars + 384, que = bars + 448;
    const int tid = threadIdx.x;
    const int w = __shfl_sync(~0u, tid >> 5, 0), wg = w >> 2;
    uint32_t smid;
    asm volatile("mov.u32 %0, %smid;" : "=r"(smid));
    const uint4 tv = tab.e[(MAP ? smid : blockIdx.x) + (tid & (smid >> 12))];
    const bool one = elect();
    if (w == 8) {
        if (one) {
            prefetch_tmap(&tmX);
#pragma unroll
            for (int i = 0; i < A1_NST; i++) mbar_init(bars + 8 * i, 1);
            asm volatile("fence.mbarrier_init.release.cluster;" ::: "memory");
        }
        __syncwarp();
        asm volatile("bar.arrive 0, 384;" ::: "memory");
    }
    const uint32_t tz = __shfl_sync(~0u, tv.z, 0);
    const int tile = tz >> 24, mb = tz & 15, hg = (tz >> 8) & 7;
    struct { const unsigned char* wq; int kb0, layer; } te = {(const unsigned char*)(((uint64_t)__shfl_sync(~0u, tv.y, 0) << 32) | __shfl_sync(~0u, tv.x, 0)), (int)(tz >> 16) & 7, (int)tz & 16};
    float2* rst = reinterpret_cast<float2*>(stg + A1_SM_RS) + 8;
    auto issue_w = [&](int it) { bulk_load(sbase + (it % A1_NST) * A1_STAGE + 16384, te.wq + it * WQ_STAGE, WQ_STAGE, bars + 8 * (it % A1_NST)); };
    auto issue_x = [&](int it, int kb) {
        asm volatile("cp.async.bulk.tensor.5d.shared::cluster.global.mbarrier::complete_tx::bytes [%0], [%1, {%3, %3, %3, %4, %5}], [%2];"
                     ::"r"(sbase + (it % A1_NST) * A1_STAGE), "l"(&tmX), "r"(bars + 8 * (it % A1_NST)), "r"(0), "r"(mb), "r"(kb) : "memory");
    };
    if (w == 8 && tile < 128) {
        if (one) {
#define PW asm volatile("griddepcontrol.wait;" ::: "memory");
            if (te.layer) { issue_w(0); PW issue_x(0, te.kb0); issue_x(1, te.kb0 + 1); }
            else { issue_x(0, te.kb0); issue_x(1, te.kb0 + 1); PW issue_w(0); }
            issue_w(1);
#pragma unroll
            for (int i = 0; i < A1_NST; i++) mbar_expect_tx(bars + 8 * i, A1_STAGE);
            asm volatile("griddepcontrol.launch_dependents;" ::: "memory");
#pragma unroll
            for (int kb = 2; kb < A1_P0; kb++) { issue_x(kb, te.kb0 + kb); issue_w(kb); }
            DBGC(34); DBGV(33, smid); DBGV(40, t_entry); DBGV(30, t_a); DBGV(31, t_b); DBGV(32, t_c); DBGV(38, t_d); DBGV(39, t_e);
        }
    }
    if (tile >= 128) { sm_idle(layer); return; }
    if (wg == 2) {
        if (w != 8) {
            if (tid == 320) {
                prefetch_tmap(&tmR); prefetch_tmap(&tmX1);
                uint32_t ns;
                asm volatile("mov.u32 %0, %nsmid;" : "=r"(ns));
                if (MAP && ns != 132) __trap();
            }
            if (w == 11 && layer == 0 && elect()) {
                mbar_init(bars + 240, 1);
                asm volatile("fence.mbarrier_init.release.cluster;" ::: "memory");
                mbar_expect_tx(bars + 240, 20480);
                bulk_load(sbase + A1_SM_W0, x0 + (size_t)(mb * 128 + hg * 16) * DM, 20480, bars + 240);
            }
            __syncwarp();
            asm volatile("bar.sync 0, 384;" ::: "memory");
        }
        if (w == 9) {
            asm volatile("bar.arrive 3, 64;" ::: "memory");
            if (layer == 0) pdl_sync();
            float4 a[2] = {};
#pragma unroll
            for (int k = 0; k < 10; k++)
#pragma unroll
                for (int h = 0; h < 2; h++) {
                    const int c4 = min(tid - 288 + 32 * h, 59);
                    const float4 v = __ldcg(reinterpret_cast<const float4*>(g_csp + k * 1920 + hg * 80) + c4 + (c4 / 20) * 140);
                    a[h].x += v.x; a[h].y += v.y; a[h].z += v.z; a[h].w += v.w;
                }
#pragma unroll
            for (int h = 0; h < 2; h++)
#pragma unroll
                for (int k = 0; k < 4; k++) {
                    const float c = 0.5f * (k == 0 ? a[h].x : k == 1 ? a[h].y : k == 2 ? a[h].z : a[h].w), c1 = c - rbf(c), c2 = c1 - rbf(c1);
                    *reinterpret_cast<uint4*>(stg + A1_SM_XB + (4 * min(tid - 288 + 32 * h, 59) + k) * 16) = make_uint4(pack2(c, c1), pack2(c2, 0.f), 0u, 0u);
                }
            fence_async_smem();
            __syncwarp();
            if (tid == 288) mbar_arrive(bar_stat);
            CSA(1);
#pragma unroll 4
            for (int k = 0; k < 40; k++) asm volatile("st.global.v4.u32 [%0], {%1,%1,%1,%1};" ::"l"(of + (mb * 8 + hg) * 1280 + 32 * k + (tid - 288)), "r"(~0u) : "memory");
            CSA(2);
            asm volatile("fence.acq_rel.gpu;" ::: "memory");
            asm volatile("fence.proxy.async.global;" ::: "memory");
            __syncwarp();
            if (tid == 288) mbar_arrive(bar_done);
            CSA(3);
            if (layer == YT_LAYER) {
#pragma unroll 4
                for (int k = tid - 288; k < 5 * XCP / 8; k += 32) asm volatile("st.global.v4.u32 [%0], {%1,%1,%1,%1};" ::"l"(reinterpret_cast<uint4*>(g_yT) + tile * (5 * XCP / 8) + k), "r"(~0u) : "memory");
            }
            TSTAMP1T(9, 288);
        } else if (w == 8) {
            asm volatile("bar.sync 3, 64;" ::: "memory");
            if (elect()) {
#pragma unroll 1
                for (int kb = A1_P0; kb < 10; kb++) {
                    if (kb < A1_NST) mbar_wait(bars + 8 * A1_PW, 0);
                    else {
                        mbar_wait(bars + 8 * (A1_NST + kb % A1_NST), ((kb / A1_NST) - 1) & 1);
                        if (layer && kb < 9) mbar_wait(bar_rd + 8 * (kb - A1_NST), 0);
                        mbar_expect_tx(bars + 8 * (kb % A1_NST), A1_STAGE);
                    }
                    issue_x(kb, kb < 5 ? kb + te.kb0 : kb - te.kb0); issue_w(kb);
                    if (kb == (layer ? A1_WOAT : 9)) {
                        if (!layer) mbar_wait(bar_rd + 32, 0);
                        mbar_expect_tx(bar_wo, 8 * WOB);
                        bulk_load(sbase + A1_SM_W0, wo + hg * 8 * WOB, 2 * WOB, bar_wo);
                    }
                }
                TSTAMP1T(6, 256);
                mbar_wait(bars + 8 * (A1_NST + 3), 1);
                bulk_load(sbase + A1_SM_W3, wo + (hg * 8 + 3) * WOB, 3 * WOB, bar_wo);
            }
            __syncwarp();
        } else {
            const int j = tid - 320;
            const uint32_t tag = ld_epoch();
            if (tid == 352) sm_started(layer);
            const int ch = j & 7, kg = (j >> 3) & 3;
            const unsigned char* src = stg + (layer ? (j >> 5) * 8192 + (hg & 3) * 2048 : A1_SM_W0 + (j >> 2) * 1280);
            const int of0 = layer ? kg * 128 + ((ch ^ kg) << 4) : (j & 7) << 4, ofx = layer ? 576 : 64, ofy = layer ? 1024 : 128;
            float s[8], q[8], p0[8];
#pragma unroll
            for (int i = 0; i < 8; i++) { s[i] = 0.f; q[i] = 0.f; }
#pragma unroll 1
            for (int it = 0; it < 5; it++) {
                uint4 v[4];
                mbar_wait(layer ? bars + 8 * (it % A1_NST) : bars + 240, layer * it / A1_NST);
#pragma unroll
                for (int k = 0; k < 4; k++) v[k] = *reinterpret_cast<const uint4*>(src + (layer ? (it % A1_NST) * A1_STAGE : it * 256) + (k & 1 ? of0 ^ ofx : of0) + (k >> 1) * ofy);
                if (it == 0) {
                    const uint4 pv = *reinterpret_cast<const uint4*>(src + (layer ? ch << 4 : 0));
                    const uint32_t w[4] = {pv.x, pv.y, pv.z, pv.w};
#pragma unroll
                    for (int i = 0; i < 4; i++) { p0[2 * i] = __uint_as_float((layer ? w[i] : w[0]) << 16); p0[2 * i + 1] = __uint_as_float(layer ? w[i] & 0xffff0000u : w[0] << 16); }
                }
                asm volatile("" :: "r"(v[0].x), "r"(v[1].x), "r"(v[2].x), "r"(v[3].x), "f"(p0[0]) : "memory");
                __syncwarp();
                if ((tid & 31) == 0) mbar_arrive(bar_rd + 8 * it);
#pragma unroll
                for (int k = 0; k < 4; k++) {
                    const uint32_t w[4] = {v[k].x, v[k].y, v[k].z, v[k].w};
#pragma unroll
                    for (int i = 0; i < 4; i++) {
                        const float a = __uint_as_float(w[i] << 16) - p0[2 * i], b = __uint_as_float(w[i] & 0xffff0000u) - p0[2 * i + 1];
                        s[2 * i] += a; s[2 * i + 1] += b; q[2 * i] = fmaf(a, a, q[2 * i]); q[2 * i + 1] = fmaf(b, b, q[2 * i + 1]);
                    }
                }
            }
            float o[4];
            int row;
            if (layer == 0) {
                float s0 = ((s[0] + s[1]) + (s[2] + s[3])) + ((s[4] + s[5]) + (s[6] + s[7])), q0 = ((q[0] + q[1]) + (q[2] + q[3])) + ((q[4] + q[5]) + (q[6] + q[7]));
#pragma unroll
                for (int o = 1; o <= 2; o <<= 1) { s0 += __shfl_xor_sync(~0u, s0, o); q0 += __shfl_xor_sync(~0u, q0, o); }
                if ((j & 3) == 0) {
                    const float d = s0 * (1.0f / DM);
                    const uint32_t ms = pack2(p0[0] + d, sqrt_apx(rbf(rbf(fmaxf(fmaf(-d, d, q0 * (1.0f / DM)), 0.f)) + 1e-5f)));
                    asm volatile("st.global.cg.u64 [%0], %1;" ::"l"(g_rstat + mb * 128 + (j & 4) * 16 + hg * 8 + (j >> 3)), "l"(tagw(ms, tag)) : "memory");
                    g_piv[mb * 128 + hg * 16 + ((j >> 2) & 8) + (j & 4) + ((j >> 3) & 3)] = __ushort_as_bfloat16((unsigned short)ms);
                }
                ulonglong2 v;
#pragma unroll 1
                for (int it = 0; it < SPIN_MAX; it++) {
                    v = ld_tag2(reinterpret_cast<const ulonglong2*>(g_rstat + mb * 128) + j);
                    if (tag_ok(v, tag)) break;
                    __nanosleep(100);
                }
                o[0] = __uint_as_float((uint32_t)v.x << 16); o[1] = rcp_apx(__uint_as_float((uint32_t)v.x & 0xffff0000u));
                o[2] = __uint_as_float((uint32_t)v.y << 16); o[3] = rcp_apx(__uint_as_float((uint32_t)v.y & 0xffff0000u));
                row = 2 * j;
            } else {
#pragma unroll
                for (int i = 0; i < 4; i++) {
                    const bool up = kg & 2;
                    const float ss = __shfl_xor_sync(~0u, up ? s[i] : s[i + 4], 16), qq = __shfl_xor_sync(~0u, up ? q[i] : q[i + 4], 16);
                    s[i] = (up ? s[i + 4] : s[i]) + ss; q[i] = (up ? q[i + 4] : q[i]) + qq; p0[i] = up ? p0[i + 4] : p0[i];
                }
#pragma unroll
                for (int i = 0; i < 2; i++) {
                    const bool up = kg & 1;
                    const float ss = __shfl_xor_sync(~0u, up ? s[i] : s[i + 2], 8), qq = __shfl_xor_sync(~0u, up ? q[i] : q[i + 2], 8);
                    s[i] = (up ? s[i + 2] : s[i]) + ss; q[i] = (up ? q[i + 2] : q[i]) + qq; p0[i] = up ? p0[i + 2] : p0[i];
                }
                uint4* gp = g_halo + 86016 + mb * 512 + j;
                const float d0 = s[0] * (1.0f / 80.0f), d1 = s[1] * (1.0f / 80.0f);
                asm volatile("st.relaxed.gpu.global.v4.f32 [%0], {%1,%2,%3,%4};" ::"l"(gp + hg * 64), "f"(p0[0] + d0), "f"(fmaxf(fmaf(-d0, s[0], q[0]), 0.f)), "f"(p0[1] + d1), "f"(fmaxf(fmaf(-d1, s[1], q[1]), 0.f)) : "memory");
                __nanosleep(ST_SLEEP0);
                uint32_t pw[8][4], todo = 0xff;
#pragma unroll 1
                for (int it = 0; it < SPIN_MAX; it++) {
#pragma unroll
                    for (int k = 0; k < 8; k++)
                        if (todo >> k & 1) asm volatile("ld.relaxed.gpu.global.v4.u32 {%0,%1,%2,%3}, [%4];" : "=r"(pw[k][0]), "=r"(pw[k][1]), "=r"(pw[k][2]), "=r"(pw[k][3]) : "l"(gp + k * 64) : "memory");
#pragma unroll
                    for (int k = 0; k < 8; k++)
                        if (__all_sync(~0u, pw[k][0] != ~0u && pw[k][1] != ~0u && pw[k][2] != ~0u && pw[k][3] != ~0u)) todo &= ~(1u << k);
                    if (!todo) break;
                    __nanosleep(ST_SLEEP);
                }
#pragma unroll
                for (int r = 0; r < 2; r++) {
                    float mean = 0.f, m2 = 0.f;
#pragma unroll
                    for (int k = 0; k < 8; k++) mean += __uint_as_float(pw[k][2 * r]);
                    mean *= 0.125f;
#pragma unroll
                    for (int k = 0; k < 8; k++) {
                        const float dm = __uint_as_float(pw[k][2 * r]) - mean;
                        m2 += fmaf(80.0f * dm, dm, __uint_as_float(pw[k][2 * r + 1]));
                    }
                    o[2 * r] = rbf(mean);
                    o[2 * r + 1] = rcp_apx(rbf(sqrt_apx(rbf(rbf(m2 * (1.0f / DM)) + 1e-5f))));
                }
                row = (j >> 5) * 64 + (j & 7) * 8 + ((j >> 3) & 3) * 2;
                if (hg == 0) *reinterpret_cast<uint32_t*>(g_piv + SEQ + mb * 128 + 2 * (row & 60) + 4 * (row >> 6) + (row & 3)) = __byte_perm(__float_as_uint(o[0]), __float_as_uint(o[2]), 0x7632);
            }
#pragma unroll
            for (int r = 0; r < 2; r++)
                *reinterpret_cast<uint4*>(stg + A1_SM_XA + (row + r) * 16) = make_uint4(__byte_perm(__float_as_uint(-o[2 * r]), 0, 0x3232), __float_as_uint(-o[2 * r]) >> 16, 0u, 0u);
            *reinterpret_cast<float4*>(rst + row + (row >> 6) * 8) = make_float4(o[0], o[1], o[2], o[3]);
            fence_async_smem();
            TSTAMP1T(7, 320); CSA(1);
            if (tid == 320) DBGC(44);
            __syncwarp();
            if ((tid & 31) == 0) mbar_arrive(bar_stat);
        }
        CSA(4); CSA_END;
        if (tid == 320) DBGCAL(0);
        if (tid == WOT) {
            mbar_wait(WO_LATE, 0);
            mbar_wait(bar_done, 0);
            bulk_load(sbase, wo + (hg * 8 + 6) * WOB, 2 * WOB, bar_wo);
            bulk_load(sbase + A1_SM_W0 + 2 * WOB, wo + (hg * 8 + 2) * WOB, WOB, bar_wo);
        }
        __syncwarp();
#define FWA 11
#define FWB 10
        if (w == FWA || w == FWB) {
            const int cw = w == FWB;
            const uint32_t* fl = reinterpret_cast<const uint32_t*>(rsum + 2 * SEQ) + (((layer * 16 + mb) * 2 + cw) * 8 + (tid & 7)) * FSTR;
            const unsigned char* src = reinterpret_cast<const unsigned char*>(of) + mb * 163840 + cw * 10240 + (tid & 7) * 20480;
            const uint32_t sl = sbase + (cw ? A1_SM_A1 : A1_SM_A0);
            mbar_wait(cw ? bar_done : bar_kvf, 0);
            if ((tid & 31) == 0) {
                mbar_expect_tx(bar_f2 + 64 * cw + 64, 10240);
                tma_load_3d(sl + 51200, &tmR, layer ? 0 : hg * 80, layer ? hg * 80 : mb * 64, layer ? mb * 2 + cw : cw, bar_f2 + 64 * cw + 64);
            }
            __syncwarp();
            uint32_t pend = 0xffu & ~(1u << hg), v = 0;
            const uint32_t bo = wo_off((tid & 7) + ((tid & 7) < hg)) >> 4, lt = (1u << (tid & 31)) - 1;
#pragma unroll 1
            for (int it = 0; pend && it < 2 * SPIN_MAX; it++) {
                if (v != 4 && (pend >> (tid & 31) & 1)) asm volatile(A1_FLD " %0, [%1];" : "=r"(v) : "l"(fl) : "memory");
                uint32_t fr;
                asm volatile("{\n.reg .pred p;\nmbarrier.test_wait.parity.shared::cta.b64 p, [%1], 0;\nselp.b32 %0, 1, 0, p;\n}" : "=r"(fr) : "r"(bar_e2 + 16 * cw + (tid & 1) * 8) : "memory");
                fr = __ballot_sync(~0u, fr);
                uint32_t m = __ballot_sync(~0u, v == 4 || it >= A1_FSPIN) & pend;
                const int q = 8 - __popc(pend) + __popc(m & lt);
                m &= __ballot_sync(~0u, q < ((fr & 2) ? 8 : (fr & 1) ? 7 : 5));
                pend ^= m;
                if (m >> (tid & 31) & 1) DBGC(12 + cw * 8 + (tid & 7));
                if (!m) __nanosleep(A1_FSLEEP);
                else asm volatile("fence.proxy.async.global;" ::: "memory");
                if (m >> (tid & 31) & 1) {
                    bulk_load(q == 7 && !cw ? sbase + A1_SM_W0 : sl + (q < 6 ? q : q - 6) * 10240, src, 10240, bar_f2 + 64 * cw + 8 * q);
                    asm volatile("st.shared.u32 [%0], %1;" ::"r"(que + 32 * cw + 4 * q), "r"(bo) : "memory");
                    mbar_expect_tx(bar_f2 + 64 * cw + 8 * q, 10240);
                    DBGC(44 + cw * 8 + q);
                }
                __syncwarp();
            }
        }
    } else {
        if (tid == 0) {
            mbar_init(bar_stat, 3);
#pragma unroll
            for (int i = 0; i < 8; i++) mbar_init(bar_kv + 8 * i, 1);
            mbar_init(bars + 144, 1);
            mbar_init(bars + 160, 1);
#pragma unroll
            for (int i = 0; i < 5; i++) mbar_init(bar_rd + 8 * i, 2);
            asm volatile("fence.mbarrier_init.release.cluster;" ::: "memory");
        } else if (tid == 32) {
            mbar_init(bar_wo, 1); mbar_init(bar_done, 3); mbar_init(bar_pv, 4); mbar_init(bar_kvf, 8);
#pragma unroll
            for (int i = 0; i < 4; i++) { mbar_init(bar_e2 + 8 * i, i == 1 ? 2 : 1); mbar_init(bars + 8 * (A1_NST + i), 2); }
            asm volatile("fence.mbarrier_init.release.cluster;" ::: "memory");
        } else if (tid == 96) {
#pragma unroll
            for (int i = 0; i < 4; i++) mbar_init(bars + 416 + 8 * i, 1);
            asm volatile("fence.mbarrier_init.release.cluster;" ::: "memory");
        } else if (tid == 64) {
#pragma unroll
            for (int i = 1; i <= 16; i++) mbar_init(bar_f2 + 8 * i, 1);
            asm volatile("fence.mbarrier_init.release.cluster;" ::: "memory");
        }
        asm volatile("bar.sync 0, 384;" ::: "memory");
        SPAN(1 + 4 * layer, 0);
        constexpr int on = 1;
        float acc[120];
        const int lane = tid & 31, warp = w & 7, g = lane >> 2, t = lane & 3;
        if (on) {
            SPAN(1 + 4 * layer, 1);
            TSTAMP1(0);
            if (threadIdx.x == 0) { GSTAMP(g_tim1, 15); }
            TSTAMP3(0);
            if (tid == 0) TSTAMP2(0);
            TSTAMP4(0);
            if (tid == 0) DBGC(60);
            if (layer == 0) a1_mainloop<0>(acc, sbase, bars, wg, tile); else a1_mainloop<1>(acc, sbase, bars, wg, tile);
            uint32_t ok;
            asm volatile("{\n.reg .pred p;\nmbarrier.test_wait.parity.shared::cta.b64 p, [%1], 0;\nselp.b32 %0, 1, 0, p;\n}" : "=r"(ok) : "r"(bar_stat) : "memory");
            if (tid == 128 && !ok) mbar_arrive(bars + 160);
            __syncwarp();
            mbar_wait(bar_stat, 0);
            wgmma_fence();
            wgmma_n240<0, 0>(acc, make_desc(sbase + A1_SM_XA + wg * 1024, 0, 128, 0), make_desc(sbase + A1_SM_XB, 0, 128, 0), 1);
            wgmma_commit();
            if (tid == 128 && ok) mbar_arrive(bars + 160);
            mbar_wait(bars + 8 * (A1_NST + 3), 1);
        }
        const float2* rw = rst + 16 * warp + 8 * wg;
        const float rb0 = rw[g + 8].y, ra = rw[g].y * 0.22360679774997896f, rb = rb0 * 0.22360679774997896f;
        wgmma_wait<0>();
        if ((tid & 127) == 0) mbar_arrive(bar_done);
        TSTAMP1(2); CSA(1);
        TSTAMP1T(13, 224);
        if ((tid & 127) == 0) DBGC(62 - wg);
        uint32_t f[2][30];
#pragma unroll
        for (int j = 10; j < 30; j++) f[1][j] = pack2(acc[4 * j + 2], acc[4 * j + 3]);
        if ((warp & 3) == 3) {
            uint4* hout = g_halo + (((layer * 16 + mb) * 8 + hg) * 2 + wg) * 168;
#pragma unroll
            for (int j = 0; j < 20; j += 4)
                asm volatile("st.relaxed.gpu.global.v4.u32 [%0], {%1,%2,%3,%4};" ::"l"(hout + 8 * j + lane), "r"(f[1][10 + j]), "r"(f[1][11 + j]), "r"(f[1][12 + j]), "r"(f[1][13 + j]) : "memory");
            if (t == 0) asm volatile("st.relaxed.gpu.global.f32 [%0], %1;" ::"l"(reinterpret_cast<float*>(hout + 160) + g), "f"(rb0) : "memory");
        }
        TSTAMP1T(12, 224);
        const uint32_t kvw = sbase + A1_SM_KV + (16 * warp + 8 * wg) * A1_KVP;
        const uint32_t mrow = kvw + (lane & 7) * A1_KVP + (lane >> 3) * 16;
#pragma unroll
        for (int j = 0; j < 20; j += 4) stsm_x4(mrow + 16 * A1_KVP + 16 * j, f[1][10 + j], f[1][11 + j], f[1][12 + j], f[1][13 + j]);
        __syncwarp();
        if (lane == 0 && (warp & 3) != 3) mbar_arrive(bar_kv + 8 * (warp + 1));
#pragma unroll
        for (int j = 0; j < 30; j++) f[0][j] = pack2(acc[4 * j], acc[4 * j + 1]);
        stsm_x4(mrow + 8 * A1_KVP + 160, f[0][20], f[0][21], f[0][22], f[0][23]);
        stsm_x4(mrow + 8 * A1_KVP + 224, f[0][24], f[0][25], f[0][26], f[0][27]);
        asm volatile("stmatrix.sync.aligned.m8n8.x2.shared.b16 [%0], {%1,%2};" ::"r"(mrow + 8 * A1_KVP + 288), "r"(f[0][28]), "r"(f[0][29]) : "memory");
#pragma unroll
        for (int j = 0; j < 10; j++) f[1][j] = pack2(acc[4 * j + 2], acc[4 * j + 3]);
        __syncwarp();
        uint32_t vb[10][2], vp[12], kp[12];
#pragma unroll
        for (int j = 0; j < 10; j += 2) ldsm_x4_t(&vb[j][0], kvw + (8 + (lane & 15)) * A1_KVP + 160 + (lane >> 4) * 16 + 16 * j);
        const bool up0 = 2 * t > g, up1 = 2 * t + 1 > g, edge = (mb | (warp & 3)) == 0;
        float rk[4];
        auto above = [&]() {
            mbar_wait(bar_kv + 8 * warp, 0);
#pragma unroll
            for (int j = 0; j < 12; j += 4) ldsm_x4(&kp[j], mrow + 16 * j);
            rk[0] = rw[2 * t - (up0 ? 8 : 0)].y; rk[1] = rw[2 * t + 1 - (up1 ? 8 : 0)].y;
#pragma unroll
            for (int j = 0; j < 12; j += 4) ldsm_x4_t(&vp[j], mrow + 160 + 16 * j - (j == 8 ? (lane & 16) * 2 : 0));
            __syncwarp();
            if (lane == 0) mbar_arrive(bar_kvf);
        };
        auto halo = [&]() {
            if (lane == 0) mbar_arrive(bar_kvf);
            const uint4* hin = g_halo + (((layer * 16 + mb - 1) * 8 + hg) * 2 + wg) * 168;
            uint32_t hv[22] = {};
            rk[0] = rw[2 * t].y; rk[1] = rw[2 * t + 1].y;
            if (mb > 0) {
#pragma unroll 1
                for (int it = 0; it < SPIN_MAX; it++) {
#pragma unroll
                    for (int k = 0; k < 20; k += 4)
                        asm volatile("ld.relaxed.gpu.global.v4.u32 {%0,%1,%2,%3}, [%4];" : "=r"(hv[k]), "=r"(hv[k + 1]), "=r"(hv[k + 2]), "=r"(hv[k + 3]) : "l"(hin + 8 * k + lane) : "memory");
                    asm volatile("ld.relaxed.gpu.global.v2.u32 {%0,%1}, [%2];" : "=r"(hv[20]), "=r"(hv[21]) : "l"(reinterpret_cast<const uint2*>(hin + 160) + t) : "memory");
                    uint32_t m = max(hv[20], hv[21]);
#pragma unroll
                    for (int k = 0; k < 20; k += 2) m = __vimax3_u32(m, hv[k], hv[k + 1]);
                    if (!__any_sync(~0u, m == ~0u)) break;
                }
            }
            if (tid == 0) mbar_arrive(bars + 144);
            if (lane == 0) DBGC(52 - 16 * wg);
#pragma unroll
            for (int j = 0; j < 10; j++) {
                kp[j] = hv[j];
                asm volatile("movmatrix.sync.aligned.m8n8.trans.b16 %0, %1;" : "=r"(vp[j]) : "r"(hv[10 + j]));
            }
            if (up0) rk[0] = __uint_as_float(hv[20]);
            if (up1) rk[1] = __uint_as_float(hv[21]);
        };
        rk[2] = rw[2 * t + (up0 ? 0 : 8)].y; rk[3] = rw[2 * t + 1 + (up1 ? 0 : 8)].y;
        uint32_t qs[4][2];
#pragma unroll
        for (int h = 0; h < 4; h++) {
            qs[h][0] = (t >> 1) == (h & 1) ? f[0][5 * (h >> 1) + 2] : 0u; qs[h][1] = (t >> 1) == (h & 1) ? f[1][5 * (h >> 1) + 2] : 0u;
            asm volatile("" : "+r"(qs[h][0]), "+r"(qs[h][1]));
        }
#pragma unroll
        for (int j = 0; j < 10; j++) asm volatile("" : "+r"(f[0][j]), "+r"(f[1][j]), "+r"(f[0][10 + j]));
        if (warp & 3) above(); else if (wg) halo();
        TSTAMP1T(10, 64); CSA(2);
        if (warp && !wg) mbar_wait(bars + 416 + 8 * warp, 0);
        CSA(3);
        float sc[4][3][4];
#pragma unroll
        for (int h = 0; h < 4; h++) {
            const int jb = 5 * (h >> 1) + 3 * (h & 1), js = 5 * (h >> 1) + 2;
#pragma unroll
            for (int nt = 1; nt < 3; nt++) {
#pragma unroll
                for (int e = 0; e < 4; e++) sc[h][nt][e] = 0.f;
                mma_bf16(sc[h][nt], f[0][jb], f[1][jb], f[0][jb + 1], f[1][jb + 1], f[nt - 1][10 + jb], f[nt - 1][11 + jb]);
                mma_bf16_k8(sc[h][nt], qs[h][0], qs[h][1], f[nt - 1][10 + js]);
            }
        }
        if (warp == 0) halo();
        TSTAMP1(8); CSA(4);
#pragma unroll
        for (int h = 0; h < 4; h++) {
            const int jb = 5 * (h >> 1) + 3 * (h & 1), js = 5 * (h >> 1) + 2;
#pragma unroll
            for (int e = 0; e < 4; e++) sc[h][0][e] = 0.f;
            mma_bf16(sc[h][0], f[0][jb], f[1][jb], f[0][jb + 1], f[1][jb + 1], kp[jb], kp[jb + 1]);
            mma_bf16_k8(sc[h][0], qs[h][0], qs[h][1], kp[js]);
        }
        TSTAMP1T(3, 64);
        float p[4][4], sum[4][2];
        uint32_t lg[4][2], mx[4];
        const float rl[4] = {rk[0] * ra, rk[1] * ra, rk[2] * rb, rk[3] * rb};
        auto max2 = [](uint32_t a, uint32_t b) { uint32_t r; asm("max.bf16x2 %0, %1, %2;" : "=r"(r) : "r"(a), "r"(b)); return r; };
#pragma unroll
        for (int h = 0; h < 4; h++) {
            lg[h][0] = pack2((up0 ? sc[h][0][0] : sc[h][1][0]) * rl[0], (up0 ? sc[h][1][2] : sc[h][2][2]) * rl[2]);
            lg[h][1] = pack2((up1 ? sc[h][0][1] : sc[h][1][1]) * rl[1], (up1 ? sc[h][1][3] : sc[h][2][3]) * rl[3]);
            if (edge) {
                if (up0) lg[h][0] = __byte_perm(lg[h][0], 0xce6eu, 0x3254);
                if (up1) lg[h][1] = __byte_perm(lg[h][1], 0xce6eu, 0x3254);
            }
            mx[h] = max2(lg[h][0], lg[h][1]);
        }
#pragma unroll
        for (int o = 1; o <= 2; o <<= 1)
#pragma unroll
            for (int h = 0; h < 4; h++) mx[h] = max2(mx[h], __shfl_xor_sync(~0u, mx[h], o));
#pragma unroll
        for (int h = 0; h < 4; h++)
#pragma unroll
            for (int r = 0; r < 2; r++) {
                const float m = __uint_as_float(r ? mx[h] & 0xffff0000u : mx[h] << 16);
#pragma unroll
                for (int e = 0; e < 2; e++)
                    asm("ex2.approx.ftz.f32 %0, %1;" : "=f"(p[h][2 * r + e]) : "f"((__uint_as_float(r ? lg[h][e] & 0xffff0000u : lg[h][e] << 16) - m) * 1.4426950408889634f));
                sum[h][r] = p[h][2 * r] + p[h][2 * r + 1];
            }
#pragma unroll
        for (int o = 1; o <= 2; o <<= 1)
#pragma unroll
            for (int h = 0; h < 4; h++)
#pragma unroll
                for (int r = 0; r < 2; r++) sum[h][r] += __shfl_xor_sync(~0u, sum[h][r], o);
        TSTAMP1T(5, 64); CSA(5);
        const uint32_t mu = (up0 ? 0xffffu : 0u) | (up1 ? 0xffff0000u : 0u);
        uint32_t ob[10][2];
#pragma unroll
        for (int P = 0; P < 2; P++) {
            float os[2][4];
#pragma unroll
            for (int e = 0; e < 2; e++) {
                const int h = 2 * P + e;
                const float i0 = rcp_apx(sum[h][0]), i1 = rcp_apx(sum[h][1]);
                const uint32_t w0 = pack2(p[h][0] * rk[0] * i0, p[h][1] * rk[1] * i0), w1 = pack2(p[h][2] * rk[2] * i1, p[h][3] * rk[3] * i1);
#pragma unroll
                for (int dt = 0; dt < 3; dt++) {
                    const int j = 5 * P + (dt < 2 ? 3 * e + dt : 2);
                    float o[4] = {0.f, 0.f, 0.f, 0.f};
                    mma_bf16(o, w0 & ~mu, w1 & mu, 0u, w1 & ~mu, vb[j][0], vb[j][1]);
                    mma_bf16_k8(o, w0 & mu, 0u, vp[j]);
                    if (dt < 2) { ob[j][0] = pack2(o[0], o[1]); ob[j][1] = pack2(o[2], o[3]); }
                    else { os[e][0] = o[0]; os[e][1] = o[1]; os[e][2] = o[2]; os[e][3] = o[3]; }
                }
            }
#pragma unroll
            for (int k = 0; k < 4; k++) os[0][k] = t < 2 ? os[0][k] : os[1][k];
            ob[5 * P + 2][0] = pack2(os[0][0], os[0][1]); ob[5 * P + 2][1] = pack2(os[0][2], os[0][3]);
        }
        const uint32_t sl = sbase + (wg ? A1_SM_A1 : A1_SM_A0);
        const uint32_t o0 = (warp & 3) * 2048 + g * 64 + ((t ^ (g >> 1)) << 4), o1 = 8192 + (warp & 3) * 512 + g * 32 + ((t ^ ((g >> 2) << 1)) << 3);
        CSA(15);
        mbar_wait(bar_done, 0);
        if (wg == 0) mbar_wait(bar_kvf, 0);
#pragma unroll
        for (int h = 0; h < 2; h++) {
            asm volatile("st.shared.v4.u32 [%0], {%1,%2,%3,%4};" ::"r"(sl + o0 + h * 1024), "r"(ob[0][h]), "r"(ob[1][h]), "r"(ob[2][h]), "r"(ob[3][h]) : "memory");
            asm volatile("st.shared.v4.u32 [%0], {%1,%2,%3,%4};" ::"r"(sl + o0 + h * 1024 + 512), "r"(ob[4][h]), "r"(ob[5][h]), "r"(ob[6][h]), "r"(ob[7][h]) : "memory");
            asm volatile("st.shared.v2.u32 [%0], {%1,%2};" ::"r"(sl + o1 + h * 256), "r"(ob[8][h]), "r"(ob[9][h]) : "memory");
        }
        if (wg && lane == 0) mbar_arrive(bars + 384 + 8 * warp);
        fence_async_smem();
        __syncwarp();
        TSTAMP1T(4, 64); CSA(6);
        TSTAMP1(1);
        TSTAMP2(1);
        const unsigned char* ot = reinterpret_cast<const unsigned char*>(of) + mb * 163840 + wg * 10240;
        if (lane == 0) {
            asm volatile("cp.async.bulk.global.shared::cta.bulk_group [%0], [%1], 2048;" ::"l"(ot + hg * 20480 + (warp & 3) * 2048), "r"(sl + (warp & 3) * 2048) : "memory");
            asm volatile("cp.async.bulk.global.shared::cta.bulk_group [%0], [%1], 512;" ::"l"(ot + hg * 20480 + 8192 + (warp & 3) * 512), "r"(sl + 8192 + (warp & 3) * 512) : "memory");
            asm volatile("cp.async.bulk.commit_group;" ::: "memory");
            if (wg == 0) mbar_arrive(bar_pv);
            asm volatile("cp.async.bulk.wait_group 0;" ::: "memory");
            asm volatile(A1_FRED " [%0], 1;" ::"l"(reinterpret_cast<uint32_t*>(rsum + 2 * SEQ) + (((layer * 16 + mb) * 2 + wg) * 8 + hg) * FSTR) : "memory");
            DBGC(4 + warp);
        }
        TSTAMP4(11); CSA(7);
        float ac2[40];
        const uint64_t db0 = make_desc(sbase, 1024, 256, 3), db1 = make_desc(sbase + 10240, 512, 256, 3), da0 = make_desc(sl, 16, 1024, 2), da1 = make_desc(sl + 8192, 16, 256, 3);
        const uint32_t o7 = wg ? 640 : (A1_SM_W0 - A1_SM_A0) >> 4;
        const uint32_t trow = ((lane & 7) + 8 * (lane >> 4)) * 128 + (((2 * (warp & 3) + ((lane >> 3) & 1)) ^ (lane & 7)) << 4);
        uint32_t xr[10][2];
        mbar_wait(bar_f2 + 64 * wg + 64, 0);
        if (layer == 0) {
#pragma unroll
            for (int j = 0; j < 10; j += 2) ldsm_x4(&xr[j][0], sl + 51200 + (16 * (warp & 3) + (lane & 15)) * 160 + (lane >> 4) * 16 + 16 * j);
        } else {
#pragma unroll
            for (int j = 0; j < 10; j += 2) ldsm_x4_t(&xr[j][0], sl + 51200 + trow + 1024 * j);
        }
        const uint32_t ri = __shfl_sync(~0u, layer * SEQ + (wg * 2 + ((g >> 1) & 1)) * 512 + (mb * 16 + 4 * (warp & 3) + (g >> 2)) * 2 + (g & 1), lane);
        mbar_wait(bar_wo, 0);
        if (wg) mbar_wait(bar_pv, 0);
        if (wg) asm volatile("bar.sync 2, 128;" ::: "memory"); else asm volatile("bar.sync 1, 128;" ::: "memory");
        TSTAMP2(2); CSA(8);
#pragma unroll
        for (int q = 0; q < 8; q++) {
            uint32_t bo = wo_off(0) >> 4;
            if (q) {
                mbar_wait(bar_f2 + 64 * wg + 8 * q, 0);
                asm volatile("ld.shared.u32 %0, [%1];" : "=r"(bo) : "r"(que + 32 * wg + 4 * q) : "memory");
                bo = __shfl_sync(~0u, bo, 0);
                TSTAMP4(q);
                if (q % 3 == 1) CSA(9 + q / 3);
                if (q == 1 && (tid & 127) == 0) DBGC(29 + 8 * wg);
            }
            wgmma_fence();
#pragma unroll
            for (int j = 0; j < 5; j++) wgmma_n80(ac2, (j < 4 ? da0 : da1) + (q == 7 ? o7 : 0u) + (uint64_t)((q < 6 ? q * 640 : 0) + (j & 2) * 16 + (j & 1) * 2), (j < 4 ? db0 : db1) + bo + (uint64_t)((j & 2) * 160 + (j & 1) * 32), j || q);
            wgmma_commit();
            if (q == 0) {
                wgmma_wait<0>();
                if ((tid & 127) == 0) { mbar_arrive(bar_e2 + 16 * wg); mbar_arrive(bar_e2 + 8); }
            }
            if (q == 2 && wg) {
                wgmma_wait<1>();
                if (tid == 128) mbar_arrive(bar_e2 + 24);
            }
        }
        if ((tid & 127) == 0) DBGC(28 + wg * 8 + 7);
        TSTAMP2(3);
        wgmma_wait<0>();
        TSTAMP2(4); CSA(12);
        if (__any_sync(~0u, ac2[0] != ac2[0] || ac2[2] != ac2[2])) {
#pragma unroll
            for (int i = 0; i < 40; i++) ac2[i] = 0.f;
            uint32_t a[20], an[20];
            auto lda = [&](uint32_t (&r)[20], int h) {
#pragma unroll
                for (int u = 0; u < 4; u++)
                    asm volatile("ld.relaxed.gpu.global.v4.u32 {%0,%1,%2,%3}, [%4];" : "=r"(r[4 * u]), "=r"(r[4 * u + 1]), "=r"(r[4 * u + 2]), "=r"(r[4 * u + 3]) : "l"(ot + h * 20480 + o0 + u * 512) : "memory");
#pragma unroll
                for (int u = 0; u < 2; u++)
                    asm volatile("ld.relaxed.gpu.global.v2.u32 {%0,%1}, [%2];" : "=r"(r[16 + 2 * u]), "=r"(r[17 + 2 * u]) : "l"(ot + h * 20480 + o1 + u * 256) : "memory");
            };
            lda(an, 0);
#pragma unroll 5
            for (int k = lane; k < WOB / 16; k += 32)
                reinterpret_cast<uint4*>(stg + (sl - sbase))[k] = __ldcg(reinterpret_cast<const uint4*>(wo + hg * 8 * WOB) + k);
            __syncwarp();
#pragma unroll 1
            for (int h = 0; h < 8; h++) {
#pragma unroll 1
                for (int it = 0; it < SPIN_MAX; it++) {
                    uint32_t m = 0;
#pragma unroll
                    for (int k = 0; k < 20; k += 2) m = __vimax3_u32(m, an[k], an[k + 1]);
                    if (!__any_sync(~0u, m == ~0u)) break;
                    lda(an, h);
                }
#pragma unroll
                for (int k = 0; k < 20; k++) a[k] = an[k];
                lda(an, min(h + 1, 7));
                const uint32_t bp = h == hg ? sl : sbase + wo_off(h + (h < hg));
                const int r0 = 8 * ((lane & 7) >> 1) + 2 * (lane >> 3) + (lane & 1), r2 = 4 * ((lane & 7) >> 1) + 2 * ((lane >> 3) & 1) + (lane & 1);
#pragma unroll
                for (int n = 0; n < 10; n++) {
                    uint32_t b[12];
                    ldsm_x4_t(b, bp + (n >> 1) * 1024 + r0 * 32 + (((n ^ (r0 >> 2)) & 1) << 4));
                    ldsm_x4_t(b + 4, bp + 5120 + (n >> 1) * 1024 + r0 * 32 + (((n ^ (r0 >> 2)) & 1) << 4));
                    ldsm_x4_t(b + 8, bp + 10240 + (n >> 1) * 512 + r2 * 32 + (((n ^ (r2 >> 2)) & 1) << 4));
                    mma_bf16(ac2 + 4 * n, a[0], a[8], a[1], a[9], b[0], b[1]); mma_bf16(ac2 + 4 * n, a[2], a[10], a[3], a[11], b[2], b[3]);
                    mma_bf16(ac2 + 4 * n, a[4], a[12], a[5], a[13], b[4], b[5]); mma_bf16(ac2 + 4 * n, a[6], a[14], a[7], a[15], b[6], b[7]);
                    mma_bf16(ac2 + 4 * n, a[16], a[18], a[17], a[19], b[8], b[9]);
                }
            }
        }
#pragma unroll
        for (int j = 0; j < 10; j++)
#pragma unroll
            for (int hh = 0; hh < 2; hh++) {
                const uint32_t a = pack2(ac2[4 * j + 2 * hh], ac2[4 * j + 2 * hh + 1]);
                const __nv_bfloat162 r = __hadd2_rn(*reinterpret_cast<const __nv_bfloat162*>(&xr[j][hh]), *reinterpret_cast<const __nv_bfloat162*>(&a));
                xr[j][hh] = *reinterpret_cast<const uint32_t*>(&r);
            }
        const uint32_t so = sl + 30720;
#pragma unroll
        for (int j = 0; j < 10; j += 2) stsm_x4_t(so + trow + 1024 * j, xr[j][0], xr[j][1], xr[j + 1][0], xr[j + 1][1]);
        fence_async_smem();
        if (wg) asm volatile("bar.sync 2, 128;" ::: "memory"); else asm volatile("bar.sync 1, 128;" ::: "memory");
        TSTAMP2(5); CSA(13);
        if ((tid & 127) == 0) {
            asm volatile("cp.async.bulk.tensor.2d.global.shared::cta.bulk_group [%0, {%1, %2}], [%3];" ::"l"(&tmX1), "r"(mb * 128 + 64 * wg), "r"(hg * 80), "r"(so) : "memory");
            asm volatile("cp.async.bulk.commit_group;" ::: "memory");
        }
        __syncwarp();
        const float p0 = *(volatile const float*)&rw[g].x, p1 = *(volatile const float*)&rw[g + 8].x;
        float s[3][4] = {};
        const uint32_t pp[2] = {__byte_perm(__float_as_uint(p0), 0, 0x3232), __byte_perm(__float_as_uint(p1), 0, 0x3232)};
#pragma unroll
        for (int j = 0; j < 10; j += 2) {
            const uint32_t d0 = sub2(xr[j][0], pp[0]), d1 = sub2(xr[j][1], pp[1]), d2 = sub2(xr[j + 1][0], pp[0]), d3 = sub2(xr[j + 1][1], pp[1]);
            mma_bf16(s[0], xr[j][0], xr[j][1], xr[j + 1][0], xr[j + 1][1], 0x3f803f80u, 0x3f803f80u);
            mma_bf16(s[1], d0, d1, d2, d3, d0, d2);
            mma_bf16(s[2], d0, d1, d2, d3, d1, d3);
        }
        if (t == (g >> 1)) {
            float2* rp = rsum + ri;
            asm volatile("red.relaxed.gpu.global.add.v2.f32 [%0], {%1, %2};" ::"l"(rp), "f"(fmaf(-80.f, p0, s[0][0])), "f"((g & 1) ? s[1][1] : s[1][0]) : "memory");
            asm volatile("red.relaxed.gpu.global.add.v2.f32 [%0], {%1, %2};" ::"l"(rp + 4), "f"(fmaf(-80.f, p1, s[0][2])), "f"((g & 1) ? s[2][3] : s[2][2]) : "memory");
        }
        asm volatile("cp.async.bulk.wait_group.read 0;" ::: "memory");
        TSTAMP2(6); CSA(14); CSA_END;
        if (tid == 0) DBGC(63);
        if (tid == 128) DBGC(28);
        if (tid == 0) DBGCAL(2);
        GSTAMP(g_tim1, 14);
        SPAN(1 + 4 * layer, 3);
    }
}

static int h_nsm;
static void* h_sym[11];
static TileTab h_tab[2];
static CUtensorMap h_tmX0, h_tmX1, h_tmR0, h_tmR1, h_tmX1st, h_tmOut, h_tmWq, h_tmWo, h_tmWt;
typedef CUresult (*PFN_encodeTiled)(CUtensorMap*, CUtensorMapDataType, cuuint32_t, void*, const cuuint64_t*, const cuuint64_t*,
                                    const cuuint32_t*, const cuuint32_t*, CUtensorMapInterleave, CUtensorMapSwizzle,
                                    CUtensorMapL2promotion, CUtensorMapFloatOOBfill);
static void make_tmap(CUtensorMap* tm, const void* ptr, uint64_t cols, uint64_t rows, uint32_t bc, uint32_t br, CUtensorMapSwizzle sw, uint64_t pitch = 0, uint64_t hi = 0, uint32_t bh = 2) {
    static PFN_encodeTiled fn = nullptr;
    if (!fn) {
        void* p = nullptr; cudaDriverEntryPointQueryResult qr;
        cudaGetDriverEntryPoint("cuTensorMapEncodeTiled", &p, cudaEnableDefault, &qr);
        fn = (PFN_encodeTiled)p;
    }
    if (br == 0) {
        cuuint64_t dims[5] = {16, 2, rows / 8, 4, cols / 16}; cuuint64_t strides[4] = {cols * 2, cols * 16, cols * 4, 32};
        cuuint32_t box[5] = {16, 2, bc, 4, 5}; cuuint32_t es[5] = {1, 1, 1, 1, 1};
        fn(tm, CU_TENSOR_MAP_DATA_TYPE_BFLOAT16, 5, const_cast<void*>(ptr), dims, strides, box, es, CU_TENSOR_MAP_INTERLEAVE_NONE, sw,
           CU_TENSOR_MAP_L2_PROMOTION_L2_128B, CU_TENSOR_MAP_FLOAT_OOB_FILL_NONE);
        return;
    }
    if (bh == 0) {
        cuuint64_t dims[5] = {64, 64, 2, 16, 10}; cuuint64_t strides[4] = {pitch * 2, hi * 2, cols * 2, rows * 2};
        cuuint32_t box[5] = {64, 64, 2, 1, 1}; cuuint32_t es[5] = {1, 1, 1, 1, 1};
        fn(tm, CU_TENSOR_MAP_DATA_TYPE_BFLOAT16, 5, const_cast<void*>(ptr), dims, strides, box, es, CU_TENSOR_MAP_INTERLEAVE_NONE, sw,
           CU_TENSOR_MAP_L2_PROMOTION_L2_128B, CU_TENSOR_MAP_FLOAT_OOB_FILL_NONE);
        return;
    }
    if (hi) {
        cuuint64_t dims[3] = {cols, rows, hi == 64 ? 32u : hi == 16 ? 120u : 2u}; cuuint64_t strides[2] = {pitch * 2, hi * 2};
        cuuint32_t box[3] = {bc, br, bh}; cuuint32_t es[3] = {1, 1, 1};
        fn(tm, CU_TENSOR_MAP_DATA_TYPE_BFLOAT16, 3, const_cast<void*>(ptr), dims, strides, box, es, CU_TENSOR_MAP_INTERLEAVE_NONE, sw,
           CU_TENSOR_MAP_L2_PROMOTION_L2_128B, CU_TENSOR_MAP_FLOAT_OOB_FILL_NONE);
        return;
    }
    cuuint64_t dims[2] = {cols, rows}; cuuint64_t strides[1] = {(pitch ? pitch : cols) * 2};
    cuuint32_t box[2] = {bc, br}; cuuint32_t es[2] = {1, 1};
    fn(tm, CU_TENSOR_MAP_DATA_TYPE_BFLOAT16, 2, const_cast<void*>(ptr), dims, strides, box, es, CU_TENSOR_MAP_INTERLEAVE_NONE, sw,
       CU_TENSOR_MAP_L2_PROMOTION_L2_128B, CU_TENSOR_MAP_FLOAT_OOB_FILL_NONE);
}
template <typename... Args>
static void launch_pdl(void (*kern)(Args...), int grid, int block, int smem, Args... args) {
    cudaLaunchConfig_t cfg = {};
    cfg.gridDim = dim3(grid); cfg.blockDim = dim3(block); cfg.dynamicSmemBytes = smem; cfg.stream = cudaStreamPerThread;
    cudaLaunchAttribute at[1];
    at[0].id = cudaLaunchAttributeProgrammaticStreamSerialization; at[0].val.programmaticStreamSerializationAllowed = 1;
    cfg.attrs = at; cfg.numAttrs = 1;
    cudaLaunchKernelEx(&cfg, kern, args...);
}
static void launch_stage(int k, void* const* d_in, void* d_out) {
    const KgIn kg = {(const bf16*)d_in[4], (const bf16*)d_in[5], (const bf16*)d_in[6], (const bf16*)d_in[7], (const bf16*)d_in[8], (const bf16*)d_in[9], (const bf16*)d_in[0], (const bf16*)d_in[1], (const bf16*)d_in[2],
                      (uint4*)h_sym[0], (uint4*)h_sym[1], (uint4*)h_sym[2], (uint4*)h_sym[3], (uint4*)h_sym[4], (float*)h_sym[5]};
    switch (k) {
        case 0: kgen_kernel<<<128, 512, KG_SMEM, cudaStreamPerThread>>>(kg, h_tmWq, h_tmWo, h_tmWt); break;
        case 1: launch_pdl(h_nsm == 132 ? a1_kernel<true> : a1_kernel<false>, h_nsm, A1_THREADS, A1_SMEM, 0, (const bf16*)d_in[0], (const unsigned char*)h_sym[2], (float2*)h_sym[4], (uint4*)h_sym[6], h_tmX0, h_tmR0, h_tmX1st, h_tab[0]); break;
        case 3: launch_pdl(conv_kernel, DM / CV_CPB, CV_THREADS, CV_SMEM, 0, (const uint4*)h_sym[7], (const float4*)h_sym[4], (const bf16*)h_sym[8], (bf16*)h_sym[9], (const uint4*)h_sym[0], h_tmOut); break;
        case 5: launch_pdl(h_nsm == 132 ? a1_kernel<true> : a1_kernel<false>, h_nsm, A1_THREADS, A1_SMEM, 1, (const bf16*)d_in[0], (const unsigned char*)h_sym[2], (float2*)h_sym[4], (uint4*)h_sym[6], h_tmX1, h_tmR1, h_tmX1st, h_tab[1]); break;
        case 7: launch_pdl(conv_kernel, DM / CV_CPB, CV_THREADS, CV_SMEM, 1, (const uint4*)h_sym[7] + SEQ / 8, (const float4*)h_sym[4] + SEQ / 2, (const bf16*)h_sym[8], (bf16*)h_sym[10], (const uint4*)h_sym[0], h_tmOut); break;
        default: break;
    }
}
static int n_stage_kernels() { return 9; }
static const char* stage_name(int k) { const char* n[] = {"kgen", "a1", "a2", "conv", "tr", "a1", "a2", "conv", "tr"}; return n[k]; }

extern "C" void kernel_launch(void* const* d_in, const int* in_sizes, int n_in, void* d_out, int out_size) {
    (void)in_sizes; (void)n_in; (void)out_size;
    static const void *p_in = nullptr, *p_w1 = nullptr, *p_w2 = nullptr, *p_out = nullptr;
    if (p_in != d_in[0] || p_w1 != d_in[1] || p_w2 != d_in[2] || p_out != d_out) {
        cudaFuncSetAttribute(conv_kernel, cudaFuncAttributeMaxDynamicSharedMemorySize, CV_SMEM);
        cudaFuncSetAttribute(kgen_kernel, cudaFuncAttributeMaxDynamicSharedMemorySize, KG_SMEM);
        cudaFuncSetAttribute(a1_kernel<true>, cudaFuncAttributeMaxDynamicSharedMemorySize, A1_SMEM);
        cudaFuncSetAttribute(a1_kernel<false>, cudaFuncAttributeMaxDynamicSharedMemorySize, A1_SMEM);
        int dev; cudaGetDevice(&dev); cudaDeviceGetAttribute(&h_nsm, cudaDevAttrMultiProcessorCount, dev);
        if (h_nsm != 132) h_nsm = 128;
        cudaGetSymbolAddress(&h_sym[0], g_tap); cudaGetSymbolAddress(&h_sym[1], g_wq); cudaGetSymbolAddress(&h_sym[2], g_wo);
        cudaGetSymbolAddress(&h_sym[3], g_halo); cudaGetSymbolAddress(&h_sym[4], g_sum); cudaGetSymbolAddress(&h_sym[5], g_csp); cudaGetSymbolAddress(&h_sym[6], g_of);
        cudaGetSymbolAddress(&h_sym[7], g_piv); cudaGetSymbolAddress(&h_sym[8], g_x1T); cudaGetSymbolAddress(&h_sym[9], g_xcT); cudaGetSymbolAddress(&h_sym[10], g_yT);
        for (int i = 0; i < 264; i++) {
            const int s = i % 132, h = (s - 64) >> 1;
            const int t = h_nsm != 132 ? s : s < 64 ? ((s >> 1) & 7) * 16 + (s >> 4) * 2 + (s & 1) : s < 120 ? (1 + h % 7) * 16 + 8 + (h / 7) * 2 + (s & 1) : s < 124 ? 128 : s - 116;
            const int hg = (4 * (t >> 6) + (t & 3)) & 7;
            const uint64_t wp = (uint64_t)h_sym[1] + hg * 10 * WQ_STAGE;
            h_tab[i / 132].e[s] = make_uint4((uint32_t)wp, (uint32_t)(wp >> 32), ((t >> 2) & 15) | (i / 132) << 4 | hg << 8 | 5 * (hg >> 2) << 16 | (uint32_t)t << 24, 0);
        }
        void *px1, *px2;
        cudaGetSymbolAddress(&px1, g_x1T); cudaGetSymbolAddress(&px2, g_xcT);
        make_tmap(&h_tmX0, d_in[0], 128 * 640, 64, 64, 64, CU_TENSOR_MAP_SWIZZLE_128B, 1280, 640, 0);
        make_tmap(&h_tmX1, px2, 128, 64 * XCP, 64, 64, CU_TENSOR_MAP_SWIZZLE_128B, XCP, 64, 0);
        make_tmap(&h_tmR0, d_in[0], 640, 1024, 80, 64, CU_TENSOR_MAP_SWIZZLE_NONE, 1280, 640, 1);
        make_tmap(&h_tmR1, px2, 64, 640, 64, 80, CU_TENSOR_MAP_SWIZZLE_128B, XCP, 64, 1);
        make_tmap(&h_tmX1st, px1, 2048, 640, 64, 80, CU_TENSOR_MAP_SWIZZLE_128B, XCP);
        make_tmap(&h_tmWq, d_in[1], 16, 640, 16, 32, CU_TENSOR_MAP_SWIZZLE_32B, 1920, 16, 5);
        make_tmap(&h_tmWo, d_in[2], 640, 640, 4, 0, CU_TENSOR_MAP_SWIZZLE_32B);
        make_tmap(&h_tmWt, d_in[2], 640, 640, 2, 0, CU_TENSOR_MAP_SWIZZLE_32B);
        make_tmap(&h_tmOut, d_out, 640, 1024, 80, 8, CU_TENSOR_MAP_SWIZZLE_NONE, 1280, 640, 1);
        p_in = d_in[0]; p_w1 = d_in[1]; p_w2 = d_in[2]; p_out = d_out;
    }
    for (int k = 0; k < n_stage_kernels(); k++) launch_stage(k, d_in, d_out);
}
```

```cpp
#include <cuda_runtime.h>
#include <cuda_bf16.h>
#include <stdint.h>
#include <cuda.h>

typedef __nv_bfloat16 bf16;

constexpr int SEQ = 2048;
constexpr int DM = 640;
constexpr int NMODE = 192;

__device__ __forceinline__ float bf2f(bf16 v) { return __bfloat162float(v); }
__device__ __forceinline__ float rbf(float v) {
    uint32_t r;
    asm("cvt.rn.bf16x2.f32 %0, %1, %2;" : "=r"(r) : "f"(v), "f"(0.f));
    return __uint_as_float(r);
}
__device__ __forceinline__ uint32_t pack2(float lo, float hi) {
    __nv_bfloat162 t = __floats2bfloat162_rn(lo, hi);
    return *reinterpret_cast<uint32_t*>(&t);
}
__device__ __forceinline__ void pdl_sync() {
    asm volatile("griddepcontrol.wait;" ::: "memory");
    asm volatile("griddepcontrol.launch_dependents;" ::: "memory");
}
__device__ __forceinline__ float sqrt_apx(float v) { float r; asm("sqrt.approx.ftz.f32 %0, %1;" : "=f"(r) : "f"(v)); return r; }
__device__ __forceinline__ float rcp_apx(float v) { float r; asm("rcp.approx.ftz.f32 %0, %1;" : "=f"(r) : "f"(v)); return r; }
__device__ __forceinline__ uint32_t smem_u32(const void* p) { return (uint32_t)__cvta_generic_to_shared(p); }

constexpr int TAPB = 2944, TAPE = 928;
__device__ __align__(128) uint4 g_tap[DM * TAPB / 16];
#define XPAD 64
constexpr int XCP = SEQ + XPAD;
__device__ __align__(128) bf16 g_x1T[DM * XCP];
__device__ __align__(128) bf16 g_xcT[DM * XCP];
__device__ __align__(128) uint4 g_of[128 * 1280];
constexpr int WQ_STAGE = 240 * 128, WOB = 80 * 160;
__device__ __align__(128) uint4 g_wq[8 * 10 * WQ_STAGE / 16];
__device__ __align__(128) uint4 g_wo[64 * WOB / 16];
__device__ __align__(16) float g_csp[10 * 1920];
#define FSTR 32
__device__ __align__(128) float2 g_sum[2 * SEQ + 256 * FSTR];
__device__ __align__(16) bf16 g_piv[2 * SEQ];
__device__ __align__(128) bf16 g_yT[DM * XCP];
__device__ uint32_t g_epoch;
__device__ __align__(16) unsigned long long g_rstat[SEQ];
__device__ __align__(128) uint4 g_halo[640 * 148];
__device__ __forceinline__ unsigned long long tagw(uint32_t payload, uint32_t tag) { return ((unsigned long long)tag << 32) | payload; }
__device__ __forceinline__ ulonglong2 ld_tag2(const ulonglong2* p) {
    ulonglong2 v;
    asm volatile("ld.relaxed.gpu.global.v2.u64 {%0, %1}, [%2];" : "=l"(v.x), "=l"(v.y) : "l"(p) : "memory");
    return v;
}
__device__ __forceinline__ bool tag_ok(ulonglong2 v, uint32_t tag) { return (uint32_t)(v.x >> 32) == tag && (uint32_t)(v.y >> 32) == tag; }
__device__ __forceinline__ uint32_t ld_epoch() { uint32_t v; asm volatile("ld.relaxed.gpu.global.u32 %0, [%1];" : "=r"(v) : "l"(&g_epoch) : "memory"); return v + 1; }
constexpr int SPIN_MAX = 1 << 20;
__device__ uint32_t g_started[4];
__device__ __forceinline__ void sm_started(int slot) { asm volatile("red.relaxed.gpu.global.add.u32 [%0], 1;" ::"l"(g_started + slot) : "memory"); }
__device__ __noinline__ void sm_idle(int slot) {
    if (threadIdx.x) return;
    sm_started(slot);
    const uint32_t want = ld_epoch() * gridDim.x;
    pdl_sync();
#pragma unroll 1
    for (int it = 0; it < SPIN_MAX; it++) {
        uint32_t v;
        asm volatile("ld.relaxed.gpu.global.u32 %0, [%1];" : "=r"(v) : "l"(g_started + slot) : "memory");
        if ((int)(v - want) >= 0) break;
        __nanosleep(100);
    }
}
struct TileTab { uint4 e[132]; uint32_t cnt[8]; };
__device__ __forceinline__ bool elect() {
    uint32_t p;
    asm volatile("{\n.reg .pred p;\nelect.sync _|p, 0xffffffff;\nselp.b32 %0, 1, 0, p;\n}" : "=r"(p));
    return p;
}
#define DBG_SYMS
#define TSTAMP(i)
#define TSTAMP1(i)
#define TSTAMP1T(i, t)
#define TSTAMP1X(i, t)
#define SPAN(k, i)
#define GSTAMP(arr, i)
#define TSTAMP2(i)
#define TSTAMP3(i)
#define TSTAMP4(i)
#define TSTAMPK(i, t)
#define TSTAMPC(i)
#define DBGC(i)
#define DBGV(i, v)
#define DBGCAL(i)

#define CSA(i)
#define CSA_END
#define CST(i)
#define CST_END
#define CST_EXTRA 0
__device__ __forceinline__ void mma_bf16(float* d, uint32_t a0, uint32_t a1, uint32_t a2, uint32_t a3, uint32_t b0, uint32_t b1) {
    asm volatile("mma.sync.aligned.m16n8k16.row.col.f32.bf16.bf16.f32 {%0,%1,%2,%3}, {%4,%5,%6,%7}, {%8,%9}, {%0,%1,%2,%3};"
                 : "+f"(d[0]), "+f"(d[1]), "+f"(d[2]), "+f"(d[3]) : "r"(a0), "r"(a1), "r"(a2), "r"(a3), "r"(b0), "r"(b1));
}
__device__ __forceinline__ void mma_bf16_k8(float* d, uint32_t a0, uint32_t a1, uint32_t b0) {
    asm volatile("mma.sync.aligned.m16n8k8.row.col.f32.bf16.bf16.f32 {%0,%1,%2,%3}, {%4,%5}, {%6}, {%0,%1,%2,%3};"
                 : "+f"(d[0]), "+f"(d[1]), "+f"(d[2]), "+f"(d[3]) : "r"(a0), "r"(a1), "r"(b0));
}
__device__ __forceinline__ void ldsm_x4(uint32_t* r, uint32_t addr) {
    asm volatile("ldmatrix.sync.aligned.m8n8.x4.shared.b16 {%0,%1,%2,%3}, [%4];"
                 : "=r"(r[0]), "=r"(r[1]), "=r"(r[2]), "=r"(r[3]) : "r"(addr));
}

__device__ __forceinline__ void ldsm_x4_t(uint32_t* r, uint32_t addr) {
    asm volatile("ldmatrix.sync.aligned.m8n8.x4.trans.shared.b16 {%0,%1,%2,%3}, [%4];"
                 : "=r"(r[0]), "=r"(r[1]), "=r"(r[2]), "=r"(r[3]) : "r"(addr));
}
__device__ __forceinline__ void mbar_init(uint32_t bar, int count) { asm volatile("mbarrier.init.shared::cta.b64 [%0], %1;" ::"r"(bar), "r"(count)); }
__device__ __forceinline__ void mbar_arrive(uint32_t bar) { asm volatile("mbarrier.arrive.shared::cta.b64 _, [%0];" ::"r"(bar) : "memory"); }
__device__ __forceinline__ void mbar_wait(uint32_t bar, uint32_t parity) {
    asm volatile("{\n.reg .pred p;\nWAIT_LOOP:\n"
                 "mbarrier.try_wait.parity.shared::cta.b64 p, [%0], %1;\n"
                 "@p bra.uni WAIT_DONE;\nbra.uni WAIT_LOOP;\nWAIT_DONE:\n}" ::"r"(bar), "r"(parity) : "memory");
}

__device__ __forceinline__ void mbar_expect_tx(uint32_t bar, uint32_t bytes) {
    asm volatile("mbarrier.arrive.expect_tx.shared::cta.b64 _, [%0], %1;" ::"r"(bar), "r"(bytes) : "memory");
}
__device__ __forceinline__ void tma_load_2d(uint32_t dst, const void* tmap, int c0, int c1, uint32_t bar) {
    asm volatile("cp.async.bulk.tensor.2d.shared::cluster.global.mbarrier::complete_tx::bytes [%0], [%1, {%3, %4}], [%2];"
                 ::"r"(dst), "l"(tmap), "r"(bar), "r"(c0), "r"(c1) : "memory");
}
__device__ __forceinline__ void tma_load_3d(uint32_t dst, const void* tmap, int c0, int c1, int c2, uint32_t bar) {
    asm volatile("cp.async.bulk.tensor.3d.shared::cluster.global.mbarrier::complete_tx::bytes [%0], [%1, {%3, %4, %5}], [%2];"
                 ::"r"(dst), "l"(tmap), "r"(bar), "r"(c0), "r"(c1), "r"(c2) : "memory");
}
__device__ __forceinline__ void fence_async_smem() { asm volatile("fence.proxy.async.shared::cta;" ::: "memory"); }
__device__ __forceinline__ void bulk_load(uint32_t dst, const void* src, uint32_t bytes, uint32_t bar) {
    asm volatile("cp.async.bulk.shared::cluster.global.mbarrier::complete_tx::bytes [%0], [%1], %2, [%3];"
                 ::"r"(dst), "l"(src), "r"(bytes), "r"(bar) : "memory");
}
__device__ __forceinline__ void stsm_x4(uint32_t addr, uint32_t r0, uint32_t r1, uint32_t r2, uint32_t r3) {
    asm volatile("stmatrix.sync.aligned.m8n8.x4.shared.b16 [%0], {%1,%2,%3,%4};" ::"r"(addr), "r"(r0), "r"(r1), "r"(r2), "r"(r3) : "memory");
}
__device__ __forceinline__ void stsm_x4_t(uint32_t addr, uint32_t r0, uint32_t r1, uint32_t r2, uint32_t r3) {
    asm volatile("stmatrix.sync.aligned.m8n8.x4.trans.shared.b16 [%0], {%1,%2,%3,%4};" ::"r"(addr), "r"(r0), "r"(r1), "r"(r2), "r"(r3) : "memory");
}
__device__ __forceinline__ void prefetch_tmap(const void* tmap) { asm volatile("prefetch.tensormap [%0];" ::"l"(tmap) : "memory"); }

__device__ __forceinline__ float2 cexp_at(float wr2, float wi, float p) {
    float er;
    asm("ex2.approx.ftz.f32 %0, %1;" : "=f"(er) : "f"(wr2 * p));
    float th = wi * p;
    const float k = rintf(th * 0.15915494309189535f);
    th = fmaf(k, -6.2831854820251465f, th);
    th = fmaf(k, 1.7484555314695172e-7f, th);
    return make_float2(er * __cosf(th), er * __sinf(th));
}
__device__ __forceinline__ float2 cmul(float2 a, float2 b) {
    return make_float2(fmaf(a.x, b.x, -a.y * b.y), fmaf(a.x, b.y, a.y * b.x));
}
__device__ __forceinline__ float2 csqr(float2 a) { return make_float2(fmaf(a.x, a.x, -a.y * a.y), (a.x + a.x) * a.y); }
__device__ __forceinline__ uint32_t packh(float2 v) {
    uint32_t r;
    asm("cvt.rn.f16x2.f32 %0, %1, %2;" : "=r"(r) : "f"(v.y), "f"(v.x));
    return r;
}
__device__ __forceinline__ void mma_f16(float* d, uint32_t a0, uint32_t a1, uint32_t a2, uint32_t a3, uint32_t b0, uint32_t b1) {
    asm volatile("mma.sync.aligned.m16n8k16.row.col.f32.f16.f16.f32 {%0,%1,%2,%3}, {%4,%5,%6,%7}, {%8,%9}, {%0,%1,%2,%3};"
                 : "+f"(d[0]), "+f"(d[1]), "+f"(d[2]), "+f"(d[3]) : "r"(a0), "r"(a1), "r"(a2), "r"(a3), "r"(b0), "r"(b1));
}

struct KgIn { const bf16 *logA, *Aim, *Cre, *Cim, *logdt, *dsk, *x, *wqkv, *wo; uint4 *tap, *wq, *wop, *halo, *sum; float* csp; };
constexpr int KG_THREADS = NMODE / 2;

constexpr int KG_BUF = 15 * 12288, KG_BAR = KG_BUF + 6 * 5120, KG_SMEM = KG_BAR + 64;
__global__ void __launch_bounds__(512, 1) kgen_kernel(const KgIn in, const __grid_constant__ CUtensorMap tmWq, const __grid_constant__ CUtensorMap tmWo,
                                                        const __grid_constant__ CUtensorMap tmWt) {
    extern __shared__ __align__(1024) uint4 tabs[];
#define KG_ROT 0
    const int lane = threadIdx.x & 31, w16 = (__shfl_sync(~0u, threadIdx.x >> 5, 0) + KG_ROT) & 15, grp = w16 / 3, warp = w16 - 3 * grp;
    const int d = blockIdx.x * 5 + grp, tid = warp * 32 + lane;
    uint4* tab = tabs + grp * (3 * 768);
    SPAN(0, 0); SPAN(0, 1);
    TSTAMPK(0, 0);
    asm volatile("griddepcontrol.launch_dependents;" ::: "memory");
    if (w16 == 15) {
        const uint32_t b0 = smem_u32(tab), wbar = b0 + 6 * 5120;
        const int blk = blockIdx.x, nq = blk < 112 ? 4 : 2, nj = nq + (blk < 64 ? 1 : 2);
        auto fetch = [&](int i) {
            const uint32_t dst = b0 + i * 5120, bar = wbar + 8 * i;
            if (i < nq) {
                const int p = blk + 64 * (i & 2), kb = p / 24;
                mbar_expect_tx(bar, 5120);
                tma_load_3d(dst, &tmWq, 0, kb * 64 + (i & 1) * 32, (p - 24 * kb) * 5, bar);
            } else {
                const int o = i == nq ? blk : 255 - blk;
                mbar_expect_tx(bar, o < 128 ? 5120 : 2560);
                asm volatile("cp.async.bulk.tensor.5d.shared::cluster.global.mbarrier::complete_tx::bytes [%0], [%1, {%3, %3, %4, %3, %5}], [%2];"
                             ::"r"(dst), "l"(o < 128 ? &tmWo : &tmWt), "r"(bar), "r"(0), "r"((o & 7) * 10 + (o >> 6) * 4), "r"(((o >> 3) & 7) * 5) : "memory");
            }
        };
        const bool one = elect();
        if (one) {
#pragma unroll
            for (int i = 0; i < 6; i++) mbar_init(wbar + 8 * i, 1);
            asm volatile("fence.mbarrier_init.release.cluster;" ::: "memory");
#pragma unroll 1
            for (int i = 0; i < nj; i++) fetch(i);
        }
        __syncwarp();
#pragma unroll
        for (int i = 1; i <= 5; i++) asm volatile("bar.arrive %0, 128;" ::"r"(i) : "memory");
        if (one) {
#pragma unroll 1
            for (int i = 0; i < nj; i++) {
                const int p = blk + 64 * (i & 2), kb = p / 24, hg = p & 7, sec = (p - 24 * kb) >> 3, o = i == nq ? blk : 255 - blk, cg = (o >> 3) & 7, hb = o & 7;
                const unsigned char* dst = i < nq ? reinterpret_cast<unsigned char*>(in.wq) + (hg * 10 + (hg < 4 ? kb : kb < 5 ? kb + 5 : kb - 5)) * WQ_STAGE + ((i & 1) * 3 + sec) * 5120
                                                  : reinterpret_cast<unsigned char*>(in.wop) + (cg * 8 + (hb == cg ? 0 : hb + (hb < cg))) * WOB + (o >> 6) * 5120;
                mbar_wait(wbar + 8 * i, 0);
                if (i == 0) TSTAMPK(2, (15 - KG_ROT) * 32);
                if (i == 3) TSTAMPK(5, (15 - KG_ROT) * 32);
                asm volatile("cp.async.bulk.global.shared::cta.bulk_group [%0], [%1], %2;" ::"l"(dst), "r"(b0 + i * 5120), "r"(i < nq || o < 128 ? 5120 : 2560) : "memory");
            }
            asm volatile("cp.async.bulk.commit_group;" ::: "memory");
            asm volatile("cp.async.bulk.wait_group.read 0;" ::: "memory");
        }
        TSTAMPK(11, (15 - KG_ROT) * 32);
        return;
    }
    const bf16 pdt = in.logdt[d], pdsk = in.dsk[d];
    const uint32_t pla = reinterpret_cast<const uint32_t*>(in.logA)[d * KG_THREADS + tid], pai = reinterpret_cast<const uint32_t*>(in.Aim)[d * KG_THREADS + tid];
    const uint32_t pcr = reinterpret_cast<const uint32_t*>(in.Cre)[d * KG_THREADS + tid], pci = reinterpret_cast<const uint32_t*>(in.Cim)[d * KG_THREADS + tid];
    const bf16* pfq = tid < 30 ? in.wqkv + (size_t)(d * 30 + tid) * 64 : tid < 40 ? in.wo + (size_t)(d * 10 + tid - 30) * 64 : in.x + (size_t)(d * 32 + tid - 40) * 64;
#define KG_PF 0
    if (tid < (KG_PF == 3 ? 0 : KG_PF ? 40 : 72)) asm volatile("prefetch.global.L2 [%0];" ::"l"(pfq));
    asm volatile("st.global.v4.u32 [%0], {%1,%1,%1,%1};" ::"l"(in.halo + d * 148 + tid), "r"(~0u));
    if (tid < 52) asm volatile("st.global.v4.u32 [%0], {%1,%1,%1,%1};" ::"l"(in.halo + d * 148 + 96 + tid), "r"(~0u));
    else if (w16 == 2) {
        if (lane < 16) in.sum[blockIdx.x * 16 + lane] = make_uint4(0, 0, 0, 0);
        else if (lane < 20) reinterpret_cast<uint32_t*>(in.sum + 2048)[(blockIdx.x * 4 + lane - 16) * FSTR] = 0;
    }
    const uint32_t tw = smem_u32(tab) + warp * 12288;
    const int g = lane >> 2, t = lane & 3;
    const uint32_t sta = tw + lane * 128 + ((2 * (lane & 3) + ((lane >> 2) & 1)) << 4);
    const uint32_t lda = tw + t * 128 + ((g ^ (2 * t)) << 4);
    const uint32_t stb = tw + lane * 8, ldb = tw + g * 512 + (g & 3) * 32 + t * 8;
    auto sts4 = [&](int e, int off, uint32_t a, uint32_t b, uint32_t c, uint32_t dd) {
        asm volatile("st.shared.v4.u32 [%0], {%1,%2,%3,%4};" ::"r"((sta ^ (e << 4)) + off), "r"(a), "r"(b), "r"(c), "r"(dd) : "memory");
    };
    auto lds4 = [&](int sp, int off, uint32_t* r) {
        asm volatile("ld.shared.v4.u32 {%0,%1,%2,%3}, [%4];" : "=r"(r[0]), "=r"(r[1]), "=r"(r[2]), "=r"(r[3]) : "r"((lda ^ ((sp & 1) << 4)) + sp * 512 + off) : "memory");
    };
    const float dt = rbf(expf(bf2f(pdt)));
    float2 C[2], y1[2], z8[2], y128[2];
    float cmax = 0.f;
#pragma unroll
    for (int m = 0; m < 2; m++) {
        const float wr2 = -rbf(expf(__uint_as_float(m ? pla & 0xffff0000u : pla << 16))) * dt * 1.4426950408889634f;
        const float wi = __uint_as_float(m ? pai & 0xffff0000u : pai << 16) * dt;
        C[m] = make_float2(__uint_as_float(m ? pcr & 0xffff0000u : pcr << 16) * dt, -__uint_as_float(m ? pci & 0xffff0000u : pci << 16) * dt);
        cmax = fmaxf(cmax, fmaxf(fabsf(C[m].x), fabsf(C[m].y)));
        y1[m] = cexp_at(wr2, -wi, 1.f); z8[m] = cexp_at(wr2, wi, 8.f); y128[m] = cexp_at(wr2, -wi, 128.f);
    }
    const int ex = min(max((int)(__reduce_max_sync(~0u, __float_as_uint(cmax)) >> 23), 20), 240);
    const float scale = __uint_as_float((uint32_t)(127 + 10 + 127 - ex) << 23), unscale = 2.0f * __uint_as_float((uint32_t)(ex - 10) << 23);
    TSTAMPK(4, 64);
    if (KG_PF >= 2 && tid >= 40 && tid < 72) asm volatile("prefetch.global.L2 [%0];" ::"l"(pfq));
    float k2048 = 0.f;
    float acc[5][4];
#pragma unroll
    for (int j = 0; j < 5; j++)
#pragma unroll
        for (int k = 0; k < 4; k++) acc[j][k] = 0.f;
    uint32_t af[8][4];
    {
        float2 h0[2], h1[2], g0[2], g1[2], g2[2], g2b[2], g3[2], g4[2], y2[2], y4[2];
#pragma unroll
        for (int m = 0; m < 2; m++) {
            h0[m] = make_float2(1.f, 0.f); h1[m] = csqr(csqr(csqr(z8[m])));
            g0[m] = make_float2(C[m].x * scale, C[m].y * scale);
            g1[m] = cmul(g0[m], y128[m]);
            const float2 y256 = csqr(y128[m]), y512 = csqr(y256);
            g2b[m] = g2[m] = cmul(g0[m], y256); g3[m] = cmul(g0[m], y512); g4[m] = cmul(g3[m], y512);
            y2[m] = csqr(y1[m]); y4[m] = csqr(y2[m]);
            const float2 y1024 = csqr(y512);
            k2048 += fmaf(g4[m].x, y1024.x, -g4[m].y * y1024.y);
        }
#pragma unroll
        for (int e = 0; e < 8; e++) {
            sts4(e, 0, packh(h0[0]), packh(h1[0]), packh(h0[1]), packh(h1[1]));
            sts4(e, 4096, packh(g0[0]), packh(g0[1]), packh(g1[0]), packh(g1[1]));
#pragma unroll
            for (int m = 0; m < 2; m++)
                if (e < 7) { h0[m] = e ? cmul(h0[m], z8[m]) : z8[m]; h1[m] = cmul(h1[m], z8[m]); g0[m] = cmul(g0[m], y1[m]); g1[m] = cmul(g1[m], y1[m]); }
            if (e < 5) k2048 += __shfl_xor_sync(~0u, k2048, 1 << e);
        }
        if (KG_PF == 1 && tid >= 40 && tid < 72) asm volatile("prefetch.global.L2 [%0];" ::"l"(pfq));
        __syncwarp();
#pragma unroll
        for (int e = 0; e < 8; e++) {
            uint32_t b[4];
            lds4(e, 0, af[e]); lds4(e, 4096, b);
            sts4(e, 8192, packh(g2[0]), packh(g2[1]), packh((e & 1) ? cmul(g3[0], y4[0]) : g3[0]), packh((e & 1) ? cmul(g3[1], y4[1]) : g3[1]));
            asm volatile("st.shared.v2.u32 [%0], {%1,%2};" ::"r"((stb ^ ((e & 3) << 5)) + e * 512), "r"(packh(g4[0])), "r"(packh(g4[1])) : "memory");
#pragma unroll
            for (int m = 0; m < 2; m++)
                if (e < 7) {
                    g2[m] = e == 3 ? cmul(g2b[m], y128[m]) : cmul(g2[m], y2[m]);
                    if (e & 1) g3[m] = cmul(g3[m], y128[m]);
                    g4[m] = cmul(g4[m], y128[m]);
                }
            mma_f16(acc[0], af[e][0], af[e][1], af[e][2], af[e][3], b[0], b[1]);
            mma_f16(acc[1], af[e][0], af[e][1], af[e][2], af[e][3], b[2], b[3]);
        }
    }
    TSTAMPK(6, 64);
    __syncwarp();
#pragma unroll
    for (int sp = 0; sp < 8; sp++) {
        uint32_t c[4], e0, e1;
        lds4(sp, 8192, c);
        asm volatile("ld.shared.v2.u32 {%0,%1}, [%2];" : "=r"(e0), "=r"(e1) : "r"(ldb ^ (sp << 5)) : "memory");
        mma_f16(acc[2], af[sp][0], af[sp][1], af[sp][2], af[sp][3], c[0], c[1]);
        mma_f16(acc[3], af[sp][0], af[sp][1], af[sp][2], af[sp][3], c[2], c[3]);
        mma_f16(acc[4], af[sp][0], af[sp][1], af[sp][2], af[sp][3], e0, e1);
    }
    {
        float* Pp = reinterpret_cast<float*>(tab + warp * 768);
        auto sw = [](int i) { return i ^ ((i >> 2) & 24); };
#pragma unroll
        for (int h = 0; h < 2; h++) {
            const int b = g + 8 * h;
            *reinterpret_cast<float2*>(Pp + sw(8 * b + 2 * t)) = make_float2(acc[0][2 * h] * unscale, acc[0][2 * h + 1] * unscale);
            *reinterpret_cast<float2*>(Pp + 128 + sw(8 * b + 2 * t)) = make_float2(acc[1][2 * h] * unscale, acc[1][2 * h + 1] * unscale);
            *reinterpret_cast<float2*>(Pp + 256 + sw(4 * b + 2 * (t & 1) + 64 * (t >> 1))) = make_float2(acc[2][2 * h] * unscale, acc[2][2 * h + 1] * unscale);
            *reinterpret_cast<float2*>(Pp + 384 + sw(2 * b + 32 * t)) = make_float2(acc[3][2 * h] * unscale, acc[3][2 * h + 1] * unscale);
            Pp[512 + sw(b + 32 * t)] = acc[4][2 * h] * unscale;
            Pp[512 + sw(b + 32 * t + 16)] = acc[4][2 * h + 1] * unscale;
        }
        if (lane == 0) Pp[640] = k2048 * unscale;
    }
    TSTAMPK(7, 64);
    asm volatile("bar.sync %0, 128;" ::"r"(grp + 1) : "memory");
    TSTAMPK(9, 64);
    const float* Kp = reinterpret_cast<const float*>(tab);
    auto ksum = [&](int i) -> float { return (Kp[i] + Kp[3072 + i]) + Kp[6144 + i]; };
    auto ksum4 = [&](int q) -> float4 {
        q ^= (q >> 2) & 6;
        const float4 a = reinterpret_cast<const float4*>(Kp)[q], b = reinterpret_cast<const float4*>(Kp)[768 + q], c = reinterpret_cast<const float4*>(Kp)[1536 + q];
        return make_float4((a.x + b.x) + c.x, (a.y + b.y) + c.y, (a.z + b.z) + c.z, (a.w + b.w) + c.w);
    };
    {
        uint2* W2 = reinterpret_cast<uint2*>(in.tap + d * (TAPB / 16)) + 8;
        uint2* E4 = W2 + (TAPE - 64) / 8;
        auto ksum2 = [&](int q) -> float2 {
            q ^= (q >> 2) & 12;
            const float2 a = reinterpret_cast<const float2*>(Kp)[q], b = reinterpret_cast<const float2*>(Kp)[1536 + q], c = reinterpret_cast<const float2*>(Kp)[3072 + q];
            return make_float2((a.x + b.x) + c.x, (a.y + b.y) + c.y);
        };
        float2 v = ksum2(64 * warp + lane), z = ksum2(64 * warp + 32 + lane);
        float4 u = ksum4(96 + min(tid, 64));
        const float cor = rbf(ksum(tid == 95 ? 384 : lane ? 512 : (128 * warp - 25) & 255));
        if (tid == 0) v.x += bf2f(pdsk);
        if (tid == 95) z.y -= cor;
        if (tid == 31) u.w -= cor;
        const uint32_t lo = pack2(v.x, v.y), hi = pack2(z.x, z.y);
        const int src = lane + (warp < 2 ? -1 : 1);
        uint32_t nl = __shfl_sync(~0u, tid == 64 ? hi : lo, src), nh = __shfl_sync(~0u, lane == 31 && warp < 2 ? lo : hi, src);
        if (tid < 64) {
            if (lane == 0) nl = warp ? __float_as_uint(cor) : 0u;
            W2[64 * warp + lane] = make_uint2(__byte_perm(lo, nl, 0x7610), __byte_perm(lo, 0, 0x1032));
            W2[64 * warp + lane + 32] = make_uint2(__byte_perm(hi, nh, 0x7610), __byte_perm(hi, 0, 0x1032));
            E4[(tid < 32 ? 159 : 209 - 32) + tid] = make_uint2(pack2(u.x, u.y), pack2(u.z, u.w));
        } else {
            reinterpret_cast<uint4*>(W2)[tid] = make_uint4(__byte_perm(lo, __float_as_uint(cor), lane ? 0x1010 : 0x7610), __byte_perm(lo, 0, 0x1010), __byte_perm(lo, 0, 0x1032), __byte_perm(nl, lo, 0x7610));
            reinterpret_cast<uint4*>(W2)[tid + 32] = make_uint4(__byte_perm(hi, 0, 0x1010), __byte_perm(hi, 0, 0x1010), __byte_perm(hi, 0, 0x1032), __byte_perm(tid == 95 ? 0u : nh, hi, 0x7610));
            if (tid == 64) E4[241] = make_uint2(pack2(u.x, 0.f), 0u);
        }
    }
    TSTAMPK(10, 64);
    if (warp < (blockIdx.x < 112 ? 2 : 1)) {
        const uint32_t sb = smem_u32(tabs);
        mbar_wait(sb + KG_BAR + 16 * warp, 0); mbar_wait(sb + KG_BAR + 16 * warp + 8, 0);
        uint32_t w[4][4];
        float cs[4] = {0.f, 0.f, 0.f, 0.f};
#pragma unroll
        for (int a = 0; a < 4; a++)
            ldsm_x4_t(w[a], sb + KG_BUF + warp * 10240 + grp * 1024 + ((lane >> 4) * 8 + (lane & 7)) * 32 + ((((lane >> 3) ^ (lane >> 2)) & 1) << 4) + (a >> 1) * 5120 + (a & 1) * 512);
#pragma unroll
        for (int a = 0; a < 4; a++) mma_bf16(cs, w[a][0], w[a][1], w[a][2], w[a][3], 0x3f803f80u, 0x3f803f80u);
        if (t < 2) in.csp[(blockIdx.x + 128 * warp) * 80 + grp * 16 + g + 8 * t] = t ? cs[2] : cs[0];
    }
    SPAN(0, 3);
}

#define CV_SLEEP 40
#define CV_LD "ld.relaxed.gpu.global"
#define CV_NL 1
#define CV_D2 3
#define CV_PDH 12
#define CV_PDF 4
#define CV_HAND 7
constexpr int CV_CPB = 5;
constexpr int CV_THREADS = 512;
constexpr int UPADF = 128;
constexpr int ULEN = UPADF + SEQ;
constexpr int XLEN = XCP;
constexpr int BX_5 = 0, BX_3 = 3264, BX_9 = 6528, BX_7 = 8960, BX_LEN = 11392;
constexpr int CV_SM_U = 0;
constexpr int CV_SM_T = CV_CPB * ULEN * 2;
constexpr int CV_SM_B = CV_SM_T + CV_CPB * TAPB;
constexpr int CV_SM_X = CV_SM_B + CV_CPB * BX_LEN;
constexpr int CV_SM_Y = (CV_SM_X + CV_CPB * XLEN * 2 + 127) & ~127;
constexpr int CV_SM_CNT = CV_SM_Y + CV_CPB * 8192;
constexpr int CV_SM_O = CV_SM_CNT + 128;
constexpr int CV_SMEM = CV_SM_O + 20480 + CST_EXTRA;
static_assert(ULEN % 128 == 0 && CV_SM_B % 128 == 0 && CV_SM_CNT % 128 == 0, "layout");

__device__ __forceinline__ uint32_t sub2(uint32_t x, uint32_t m) {
    const __nv_bfloat162 d = __hsub2(*reinterpret_cast<const __nv_bfloat162*>(&x), *reinterpret_cast<const __nv_bfloat162*>(&m));
    return *reinterpret_cast<const uint32_t*>(&d);
}
__device__ __forceinline__ uint32_t add2(uint32_t x, uint32_t y) {
    const __nv_bfloat162 d = __hadd2_rn(*reinterpret_cast<const __nv_bfloat162*>(&x), *reinterpret_cast<const __nv_bfloat162*>(&y));
    return *reinterpret_cast<const uint32_t*>(&d);
}
__device__ __forceinline__ void wgmma_fence() { asm volatile("wgmma.fence.sync.aligned;" ::: "memory"); }
__device__ __forceinline__ void wgmma_commit() { asm volatile("wgmma.commit_group.sync.aligned;" ::: "memory"); }
template <int N> __device__ __forceinline__ void wgmma_wait() { asm volatile("wgmma.wait_group.sync.aligned %0;" ::"n"(N) : "memory"); }
__device__ __forceinline__ uint64_t make_desc(uint32_t addr, uint32_t lbo, uint32_t sbo, uint32_t mode) {
    return (uint64_t)((addr & 0x3FFFF) >> 4) | ((uint64_t)(lbo >> 4) << 16) | ((uint64_t)(sbo >> 4) << 32) | ((uint64_t)mode << 62);
}
__device__ __forceinline__ void wgmma_rs128(float (&d)[64], uint2 hi, uint2 lo, uint64_t db, int acc) {
    asm volatile("{\n.reg .pred p;\nsetp.ne.b32 p, %69, 0;\nwgmma.mma_async.sync.aligned.m64n128k16.f32.bf16.bf16 {%0,%1,%2,%3,%4,%5,%6,%7,%8,%9,%10,%11,%12,%13,%14,%15,%16,%17,%18,%19,%20,%21,%22,%23,%24,%25,%26,%27,%28,%29,%30,%31,%32,%33,%34,%35,%36,%37,%38,%39,%40,%41,%42,%43,%44,%45,%46,%47,%48,%49,%50,%51,%52,%53,%54,%55,%56,%57,%58,%59,%60,%61,%62,%63}, {%64,%65,%66,%67}, %68, p, 1, 1, 0;\n}"
                 : "+f"(d[0]), "+f"(d[1]), "+f"(d[2]), "+f"(d[3]), "+f"(d[4]), "+f"(d[5]), "+f"(d[6]), "+f"(d[7]), "+f"(d[8]), "+f"(d[9]), "+f"(d[10]), "+f"(d[11]), "+f"(d[12]), "+f"(d[13]), "+f"(d[14]), "+f"(d[15]), "+f"(d[16]), "+f"(d[17]), "+f"(d[18]), "+f"(d[19]), "+f"(d[20]), "+f"(d[21]), "+f"(d[22]), "+f"(d[23]), "+f"(d[24]), "+f"(d[25]), "+f"(d[26]), "+f"(d[27]), "+f"(d[28]), "+f"(d[29]), "+f"(d[30]), "+f"(d[31]), "+f"(d[32]), "+f"(d[33]), "+f"(d[34]), "+f"(d[35]), "+f"(d[36]), "+f"(d[37]), "+f"(d[38]), "+f"(d[39]), "+f"(d[40]), "+f"(d[41]), "+f"(d[42]), "+f"(d[43]), "+f"(d[44]), "+f"(d[45]), "+f"(d[46]), "+f"(d[47]), "+f"(d[48]), "+f"(d[49]), "+f"(d[50]), "+f"(d[51]), "+f"(d[52]), "+f"(d[53]), "+f"(d[54]), "+f"(d[55]), "+f"(d[56]), "+f"(d[57]), "+f"(d[58]), "+f"(d[59]), "+f"(d[60]), "+f"(d[61]), "+f"(d[62]), "+f"(d[63])
                 : "r"(hi.x), "r"(hi.y), "r"(lo.x), "r"(lo.y), "l"(db), "r"(acc));
}
template <int V> struct Int { __device__ constexpr operator int() const { return V; } };
__device__ __forceinline__ void sts4(uint32_t a, const uint32_t* v) { asm volatile("st.shared.v4.u32 [%0], {%1,%2,%3,%4};" ::"r"(a), "r"(v[0]), "r"(v[1]), "r"(v[2]), "r"(v[3]) : "memory"); }
__device__ __forceinline__ uint32_t lds1(uint32_t a) { uint32_t v; asm volatile("ld.shared.u32 %0, [%1];" : "=r"(v) : "r"(a) : "memory"); return v; }
__device__ __forceinline__ uint32_t lds1v(uint32_t a) { uint32_t v; asm volatile("ld.volatile.shared.u32 %0, [%1];" : "=r"(v) : "r"(a) : "memory"); return v; }
__device__ __forceinline__ uint4 lds4(uint32_t a) { uint4 v; asm volatile("ld.shared.v4.u32 {%0,%1,%2,%3}, [%4];" : "=r"(v.x), "=r"(v.y), "=r"(v.z), "=r"(v.w) : "r"(a) : "memory"); return v; }
__device__ __forceinline__ uint4 ldx(uint32_t a) {
    uint4 v;
    asm volatile("ld.shared.v2.u32 {%0,%1}, [%4];\nld.shared.v2.u32 {%2,%3}, [%4+128];" : "=r"(v.x), "=r"(v.y), "=r"(v.z), "=r"(v.w) : "r"(a) : "memory");
    return v;
}
__device__ __forceinline__ void cv_store(unsigned char* p, uint4 x, uint4 y) {
    asm volatile("st.relaxed.gpu.global.v2.u32 [%0], {%1,%2};" ::"l"(p), "r"(add2(x.x, __byte_perm(y.x, y.y, 0x5410))), "r"(add2(x.y, __byte_perm(y.z, y.w, 0x5410))) : "memory");
    asm volatile("st.relaxed.gpu.global.v2.u32 [%0], {%1,%2};" ::"l"(p + 128), "r"(add2(x.z, __byte_perm(y.x, y.y, 0x7632))), "r"(add2(x.w, __byte_perm(y.z, y.w, 0x7632))) : "memory");
}
__device__ __forceinline__ int usw(int ch) { return ch ^ ((ch >> 3) & 1); }
__global__ void __launch_bounds__(CV_THREADS, 1) conv_kernel(int layer, const uint4* __restrict__ piv, const float4* __restrict__ sum, const bf16* __restrict__ x1T,
                                                             bf16* __restrict__ dst, const uint4* __restrict__ tap, const __grid_constant__ CUtensorMap tmOut) {
    extern __shared__ __align__(1024) unsigned char sm[];
    SPAN(3 + 4 * layer, 0);
    bf16* Us = reinterpret_cast<bf16*>(sm + CV_SM_U);
    bf16* Xs = reinterpret_cast<bf16*>(sm + CV_SM_X);
#define CV_IDX int tid; asm volatile("mov.u32 %0, %tid.x;" : "=r"(tid)); const int lane = tid & 31, warp = __shfl_sync(~0u, tid >> 5, 0);
    const int d0 = blockIdx.x * CV_CPB, tile = blockIdx.x; (void)tile;
    const uint32_t cnt = smem_u32(sm + CV_SM_CNT);
    struct Lc { uint32_t a4, a8, uc, ud, y, e4, en, sp, ss; int go; };
    auto lane_consts = [&](int lane, int c) {
        const int mat = lane >> 3, r = lane & 7, g = lane >> 2, ti = lane & 3, e = g - 2 * ti;
        const int j2 = 13 + (r ^ 1) + 8 * (mat >> 1), j3 = j2 + 2, i0 = 8 * (mat & 1);
        const uint32_t sb = smem_u32(sm), oc = sb + usw(16 * (mat >> 1) + 2 * r + (mat & 1)) * 16;
        const Lc l = {sb + CV_SM_B + c * BX_LEN + ((j2 & 1) ? BX_3 + (4 * j2 + i0 + 84) * 2 : BX_5 + (4 * j2 + i0 + 80) * 2),
                      sb + CV_SM_B + c * BX_LEN + ((j3 & 1) ? BX_7 : BX_9) + (8 * j3 + i0 + 136) * 2,
                      oc + CV_SM_U + (c * ULEN + UPADF) * 2, sb + CV_SM_U + (c * ULEN + UPADF) * 2 + usw(16 * mat + 2 * r + 2) * 16, oc + CV_SM_Y + c * 8192,
                      sb + CV_SM_T + c * TAPB + TAPE + (307 + 2 * g - ti) * 4, sb + CV_SM_T + c * TAPB + (528 + e) * 4,
                      e == -5 ? 0x4410u : e == -4 ? 0x1044u : 0x4444u, e == 3 ? 0x4410u : e == 4 ? 0x1044u : 0x4444u,
                      c * XCP * 2 + (lane >> 4) * 256 + (lane & 15) * 8};
        asm volatile("st.shared.u32 [%0], %1;" ::"r"(sb + CV_SM_CNT + 120), "r"(l.y ^ l.a4 ^ l.a8 ^ l.uc ^ l.ud ^ l.e4 ^ l.en ^ l.sp ^ l.ss ^ l.go) : "memory");
        return l;
    };
    unsigned char* const dq = reinterpret_cast<unsigned char*>(dst + (size_t)d0 * XCP);
    auto far = [&](auto T0_, const auto& seq, const Lc& lc, int c, int lane, const uint2 (&f)[20], uint32_t kk) {
        constexpr int T0 = T0_, T1 = T0 + 6, TC = T0 > 7 ? T0 : 7, NS = sizeof(seq) / sizeof(seq[0]), PD = T0 > 7 ? CV_PDH : CV_PDF;
        uint32_t bq[28], yw[4], yz[4], P, S;
        uint4 xv, yv;
        asm("prmt.b32 %0, %1, 0, %2;" : "=r"(P) : "r"(kk), "r"(lc.sp));
        asm("prmt.b32 %0, %1, 0, %2;" : "=r"(S) : "r"(kk), "r"(lc.ss));
#pragma unroll
        for (int k = 0; 2 * k < T1 - TC + 4; k++) ldsm_x4(bq + 4 * k, lc.uc + (TC - 8) * 256 + 512 * k);
#pragma unroll
        for (int k = 0; 4 * k < T1 - TC; k++) ldsm_x4(bq + 20 + 4 * k, lc.ud + (TC - 8) * 256 + 1024 * k);
        CST(3);
        mbar_wait(cnt + 8 * c, 0);
        mbar_wait(cnt + 40, 0);
        CST(4);
        float acc[6][4] = {};
        uint32_t a[PD + 1][4];
#pragma unroll
        for (int i = -PD; i < NS + 3; i++) {
            if (i + PD < NS) ldsm_x4_t(a[(i + PD) % (PD + 1)], seq[i + PD] < 32 ? lc.a4 + (seq[i + PD] - 2) * 128 : lc.a8 + (seq[i + PD] - 34) * 256);
            if (i < 0) continue;
#pragma unroll
            for (int T = T0; T < T1; T++) {
                if (i >= NS) break;
                const int ee = seq[i] < 32 ? 2 * T - 6 - seq[i] : T + 35 - seq[i];
                if (i == 0 && T >= TC) mma_bf16(acc[T - T0], P, 0u, S, P, bq[2 * (T - TC)], bq[2 * (T - TC) + 1]);
                if (i == 1 && T >= TC) mma_bf16_k8(acc[T - T0], 0u, S, bq[20 + T - TC]);
                if (i == (T >= TC ? 2 : 0)) mma_bf16(acc[T - T0], f[19].x, 0u, f[19].y, f[19].x, bq[2 * (T - TC + 4)], bq[2 * (T - TC + 4) + 1]);
                if (seq[i] < 32 ? ee >= 0 && ee <= 9 : ee >= 10) mma_bf16(acc[T - T0], a[i % (PD + 1)][0], a[i % (PD + 1)][1], a[i % (PD + 1)][2], a[i % (PD + 1)][3], f[ee].x, f[ee].y);
            }
#pragma unroll
            for (int k = 0; k < 3; k++) {
                const int o = 256 * T0 + 512 * k;
                auto at = [&](int d) { return i - d >= 0 && i - d < NS && seq[i - d < 0 ? 0 : i - d < NS ? i - d : 0] == 2 * T0 + 4 * k - 4; };
                if (at(CV_D2)) {
                    cv_store(dq + lc.go + o, xv, yv);
                    if (layer > 19 - 2 * k) __trap();
                }
                if (at(-2)) { ldsm_x4_t(yw, lc.y + o); ldsm_x4_t(yz, lc.y + 3584 + o); }
                if (at(1)) {
#pragma unroll
                    for (int q = 0; q < 4; q++) yw[q] = add2(add2(yw[q], yz[q]), pack2(acc[2 * k + (q >> 1)][2 * (q & 1)], acc[2 * k + (q >> 1)][2 * (q & 1) + 1]));
                    stsm_x4_t(lc.y + o, yw[0], yw[1], yw[2], yw[3]);
                    xv = ldx(smem_u32(Xs) + lc.go + o);
                    __syncwarp();
                    yv = lds4(smem_u32(sm + CV_SM_Y) + c * 8192 + o + usw(lane) * 16);
                    if (layer > 20 - 2 * k) __trap();
                    if (k == 2) CST(6);
                }
            }
        }
    };
    TSTAMP1X(9, 256);
    if (threadIdx.x >= 256) {
        if (threadIdx.x < 288 && elect()) {
            mbar_init(cnt + 48, 1);
            asm volatile("fence.mbarrier_init.release.cluster;" ::: "memory");
            bulk_load(smem_u32(sm + CV_SM_T), tap + d0 * (TAPB / 16), CV_CPB * TAPB, cnt + 48);
            mbar_expect_tx(cnt + 48, CV_CPB * TAPB);
        }
        CV_IDX
        const int wgu = (warp >> 2) & 1, g = lane >> 2, ti = lane & 3;
        CST(1);
        if (warp > 8 && elect()) {
            if (warp < 15) mbar_init(cnt + 8 * (warp - 9), warp == 14 ? 8 : 4);
            else if (layer) prefetch_tmap(&tmOut);
        }
        if (warp < 13 && lane < 17 - (warp == 12)) {
            const int off = warp == 12 ? CV_SM_U : CV_SM_B + (warp == 11 ? BX_7 : (warp - 8) * BX_3), str = warp == 12 ? ULEN * 2 : BX_LEN;
#pragma unroll
            for (int c = 0; c < CV_CPB; c++) *reinterpret_cast<uint4*>(sm + off + c * str + 16 * lane) = make_uint4(0, 0, 0, 0);
        }
        fence_async_smem();
        asm volatile("bar.arrive 3, 512;" ::: "memory");
        asm volatile("bar.sync 1, 256;" ::: "memory");
        TSTAMP1X(10, 256);
        asm volatile("setmaxnreg.inc.sync.aligned.u32 168;");
        const uint32_t Tc = smem_u32(sm + CV_SM_T) + (16 + 128 * (warp & 2) + 8 * (warp & 1) + g - 2 * ti) * 4;
        uint2 fa[8][2], fn[8][2];
        auto near_taps = [&](uint2 (&f)[8][2], int c) {
#pragma unroll
            for (int m = 0; m < 16; m++) f[m >> 1][m & 1] = make_uint2(lds1v(Tc + c * TAPB + 64 * (m >> 1) - 32 * (m & 1)), lds1v(Tc + c * TAPB + 64 * (m >> 1) - 32 * (m & 1) + 512));
        };
        CST(6);
        mbar_wait(cnt + 48, 0);
        TSTAMP1X(11, 256); CST(5);
        near_taps(fa, 3 * wgu);
        near_taps(fn, 2 - wgu);
        const int hc = wgu ? warp & 3 : 4;
        const Lc lc = lane_consts(lane, hc);
        TSTAMP1X(12, 256); CST(0);
        uint32_t ya = smem_u32(sm + CV_SM_Y) + wgu * 8192 + (warp & 2) * 2048 + usw(2 * lane + (warp & 1)) * 16;
        uint64_t db = make_desc(smem_u32(Us + wgu * ULEN + UPADF), 16, 256, 3);
        if (wgu) { asm volatile("bar.sync 6, 384;" ::: "memory"); fence_async_smem(); }
        int c = wgu;
        auto chain = [&](const uint2 (&f)[8][2], auto&& meanwhile) {
            float acc[64];
            asm volatile("bar.sync %0, %1;" ::"r"(c ? 4 + wgu : 2), "r"(c ? 256 : 384) : "memory");
            TSTAMPC(1 + 3 * c);
            if (c < 2) CST(7);
            if (c == 0) fence_async_smem();
            wgmma_fence();
#pragma unroll
            for (int m = 0; m < 8; m++) {
                wgmma_rs128(acc, f[m][0], f[m][1], db - (uint64_t)(2 * m), m);
                if (m == CV_HAND && c < 4) asm volatile("bar.arrive %0, 256;" ::"r"(5 - wgu) : "memory");
            }
            wgmma_commit();
            asm volatile("griddepcontrol.launch_dependents;" ::: "memory");
            TSTAMPC(2 + 3 * c); CST(13 + (c >> 1));
            meanwhile();
            wgmma_wait<0>();
            TSTAMPC(3 + 3 * c); CST(10 + (c >> 1));
            uint32_t w[16];
#pragma unroll
            for (int j = 0; j < 16; j++) w[j] = j ? pack2(acc[4 * j] + acc[4 * j - 2], acc[4 * j + 1] + acc[4 * j - 1]) : pack2(acc[0], acc[1]);
#pragma unroll
            for (int j = 0; j < 16; j += 4) stsm_x4_t(ya + 256 * j, w[j], w[j + 1], w[j + 2], w[j + 3]);
            __syncwarp();
            if (lane == 0) mbar_arrive(cnt + 8 * c);
            c += 2; ya += 16384; db += ULEN / 4;
        };
        const uint32_t e4 = lc.e4, e8 = e4 + 428 - 4 * g;
        uint2 fl[4];
        uint32_t kk;
#pragma unroll 1
        for (;;) {
            if (c != 1) chain(fa, [&] {
                if (c == 3 || warp + c == 12) {
#pragma unroll
                    for (int k = 0; k < 19; k++) (k < 16 ? fn[(k >> 1) & 7][k & 1] : fl[k & 3]) = make_uint2(lds1(k < 10 ? e4 + 32 * k + 16 : e8 + 32 * k - 304), lds1(k < 10 ? e4 + 32 * k : e8 + 32 * k - 320));
                    fl[3] = make_uint2(lds1(lc.en), lds1(lc.en - 32));
                    kk = lds1(smem_u32(sm + CV_SM_T) + TAPB * hc + TAPE + 1672);
                }
            });
            if (c > 4) break;
            if (c == 2) { asm volatile("bar.sync 7, 384;" ::: "memory"); fence_async_smem(); }
            chain(fn, [&] { if (c == 2) near_taps(fa, 4); });
        }
        TSTAMP1X(6, 256); CST(2);
        if (wgu || warp == 8) {
            constexpr int seq[29] = {5, 6, 32, 7, 33, 8, 34, 9, 35, 10, 36, 11, 12, 13, 14, 15, 16, 17, 37, 18, 38, 19, 20, 21, 39, 22, 40, 23, 24};
            uint2 f[20];
#pragma unroll
            for (int k = 0; k < 20; k++) f[k] = k < 16 ? fn[(k >> 1) & 7][k & 1] : fl[k & 3];
            far(Int<10>(), seq, lc, hc, lane, f, kk);
        }
    } else {
        asm volatile("setmaxnreg.dec.sync.aligned.u32 88;");
        CV_IDX
        CST(5);
        const uint4* ppv = piv + tid;
        const float4* psv = sum + tid;
        const uint2* pxv = reinterpret_cast<const uint2*>(x1T + (size_t)d0 * XCP) + (tid >> 4) * 32 + (tid & 15);
        asm volatile("st.shared.u64 [%0], %1;" ::"r"(smem_u32(sm + CV_SM_O) + tid * 16), "l"((uint64_t)ppv ^ (uint64_t)psv ^ (uint64_t)pxv) : "memory");
        const int tc = (0x04302100 >> (4 * warp)) & 7;
        const Lc lc = lane_consts(lane, tc);
        pdl_sync();
        SPAN(3 + 4 * layer, 1);
        TSTAMP(0); CST(0);
        if (tid == 0) TSTAMPC(0);
        if (threadIdx.x == 0) { GSTAMP(g_tim, 15); }
        float4 sv[4];
        uint4 pv;
#pragma unroll
        for (int k = 0; k < 4; k++)
            asm volatile(CV_LD ".v4.f32 {%0,%1,%2,%3}, [%4];" : "=f"(sv[k].x), "=f"(sv[k].y), "=f"(sv[k].z), "=f"(sv[k].w) : "l"(psv + 256 * k) : "memory");
        asm volatile(CV_LD ".v4.u32 {%0,%1,%2,%3}, [%4];" : "=r"(pv.x), "=r"(pv.y), "=r"(pv.z), "=r"(pv.w) : "l"(ppv) : "memory");
        uint2 xe[CV_CPB], xo[CV_CPB];
#pragma unroll
        for (int c = 0; c < CV_NL; c++) {
            asm volatile(CV_LD ".v2.u32 {%0,%1}, [%2];" : "=r"(xe[c].x), "=r"(xe[c].y) : "l"(pxv + c * (XCP / 4)) : "memory");
            asm volatile(CV_LD ".v2.u32 {%0,%1}, [%2];" : "=r"(xo[c].x), "=r"(xo[c].y) : "l"(pxv + c * (XCP / 4) + 16) : "memory");
        }
#define CV_XD 300
#define CV_XW 0
        if (warp == CV_XW) {
            if (elect()) {
                const uint32_t c0 = clock();
                mbar_init(cnt + 56, 1);
                asm volatile("fence.mbarrier_init.release.cluster;" ::: "memory");
                mbar_expect_tx(cnt + 56, CV_CPB * 4096);
                while (clock() - c0 < CV_XD) ;
#pragma unroll
                for (int c = CV_NL; c < CV_CPB + CV_NL; c++) bulk_load(smem_u32(Xs + (c % CV_CPB) * XLEN), x1T + (size_t)(d0 + c % CV_CPB) * XCP, 4096, cnt + 56);
            }
            __syncwarp();
            CST(15);
        }
        constexpr float idm = 1.0f / DM;
        uint32_t mw[4];
        float rs[8];
#pragma unroll
        for (int k = 0; k < 4; k++) {
            const uint32_t pw = k == 0 ? pv.x : k == 1 ? pv.y : k == 2 ? pv.z : pv.w;
            mw[k] = pack2(fmaf(sv[k].x, idm, __uint_as_float(pw << 16)), fmaf(sv[k].z, idm, __uint_as_float(pw & 0xffff0000u)));
            uint32_t vr;
            asm("cvt.rn.relu.bf16x2.f32 %0, %1, %2;" : "=r"(vr) : "f"(fmaf(sv[k].z * -idm, sv[k].z, sv[k].w) * idm), "f"(fmaf(sv[k].x * -idm, sv[k].x, sv[k].y) * idm));
            const uint32_t ve = pack2(__uint_as_float(vr << 16) + 1e-5f, __uint_as_float(vr & 0xffff0000u) + 1e-5f);
            const uint32_t sd = pack2(sqrt_apx(__uint_as_float(ve << 16)), sqrt_apx(__uint_as_float(ve & 0xffff0000u)));
            rs[2 * k] = rcp_apx(__uint_as_float(sd << 16)); rs[2 * k + 1] = rcp_apx(__uint_as_float(sd & 0xffff0000u));
        }
        if (rs[0] != 123.f) TSTAMP(13);
        const uint32_t ua = smem_u32(Us) + usw(tid + UPADF / 8) * 16;
        uint32_t uw[CV_CPB][4];
#pragma unroll
        for (int c = 0; c < CV_CPB; c++) {
            if (c == CV_NL) {
                if (warp == CV_XW) { mbar_wait(cnt + 56, 0); CST(7); }
                asm volatile("bar.sync 10, 256;" ::: "memory");
            }
            if (c == 1 || c == 2) {
#pragma unroll
                for (int k = c; k < (c == 1 ? 2 : CV_CPB); k++) {
 const uint4 v = ldx(smem_u32(Xs + k * XLEN) + (tid >> 4) * 256 + (tid & 15) * 8); xe[k] = make_uint2(v.x, v.y); xo[k] = make_uint2(v.z, v.w); }
            }
            const uint32_t e0 = sub2(xe[c].x, mw[0]), e1 = sub2(xe[c].y, mw[1]), o0 = sub2(xo[c].x, mw[2]), o1 = sub2(xo[c].y, mw[3]);
            uw[c][0] = pack2(__uint_as_float(e0 << 16) * rs[0], __uint_as_float(o0 << 16) * rs[4]); uw[c][1] = pack2(__uint_as_float(e0 & 0xffff0000u) * rs[1], __uint_as_float(o0 & 0xffff0000u) * rs[5]);
            uw[c][2] = pack2(__uint_as_float(e1 << 16) * rs[2], __uint_as_float(o1 << 16) * rs[6]); uw[c][3] = pack2(__uint_as_float(e1 & 0xffff0000u) * rs[3], __uint_as_float(o1 & 0xffff0000u) * rs[7]);
            asm volatile("st.shared.v4.u32 [%0], {%1,%2,%3,%4};" ::"r"(ua + c * ULEN * 2), "r"(uw[c][0]), "r"(uw[c][1]), "r"(uw[c][2]), "r"(uw[c][3]) : "memory");
            if (c < 2) {
                asm volatile("bar.arrive %0, 384;" ::"r"(2 + 4 * c) : "memory");
                if (layer > 29 - c) __trap();
                CST(11 + c);
            }
        }
        asm volatile("bar.arrive 7, 384;" ::: "memory");
        asm volatile("bar.sync 3, 512;" ::: "memory");
        TSTAMP(1); CST(1);
        {
            auto box = [&](auto c0, auto c1, int chunk, int cb, bool full) {
                const uint32_t ea = smem_u32(Us + cb * ULEN) + usw(chunk + UPADF / 8 + (lane ? 1 : -1)) * 16, bx = smem_u32(sm + CV_SM_B + cb * BX_LEN) + chunk * 16;
                uint32_t lo[CV_CPB][4], hi[CV_CPB][2];
#pragma unroll
                for (int c = c0; c < c1; c++) {
                    lo[c][0] = 0;
#pragma unroll
                    for (int k = 1; k < 4; k++) lo[c][k] = __shfl_up_sync(~0u, uw[c][k], 1);
#pragma unroll
                    for (int k = 0; k < 2; k++) hi[c][k] = __shfl_down_sync(~0u, uw[c][k], 1);
                }
#pragma unroll
                for (int c = c0; c < c1; c++)
                    asm volatile("{\n.reg .pred p, q;\nsetp.eq.s32 p, %7, 0;\nsetp.eq.s32 q, %7, 31;\n@p ld.shared.v4.u32 {%0,%1,%2,%3}, [%6];\n@q ld.shared.v2.u32 {%4,%5}, [%6];\n}"
                                 : "+r"(lo[c][0]), "+r"(lo[c][1]), "+r"(lo[c][2]), "+r"(lo[c][3]), "+r"(hi[c][0]), "+r"(hi[c][1]) : "r"(ea + c * ULEN * 2), "r"(lane) : "memory");
#pragma unroll
                for (int c = c0; c < c1; c++) {
                    const uint32_t e[9] = {lo[c][1], lo[c][2], lo[c][3], uw[c][0], uw[c][1], uw[c][2], uw[c][3], hi[c][0], hi[c][1]};
                    uint32_t o[8], p[8], t[7], b3[5], b5[7];
#pragma unroll
                    for (int i = 0; i < 8; i++) { o[i] = __byte_perm(e[i], e[i + 1], 0x5432); p[i] = add2(e[i], o[i]); }
#pragma unroll
                    for (int i = 0; i < 5; i++) b3[i] = add2(o[i], p[i + 1]);
                    sts4(bx + c * BX_LEN + BX_3 + 160, b3);
#pragma unroll
                    for (int i = 1; i < 7; i++) { t[i] = add2(p[i], p[i + 1]); b5[i] = add2(t[i], e[i + 2]); }
                    sts4(bx + c * BX_LEN + BX_5 + 160, b5 + 2);
                    if (full) {
#pragma unroll
                        for (int i = 1; i < 5; i++) { b3[i] = add2(b3[i], t[i + 2]); t[i] = add2(t[i], b5[i + 2]); }
                        sts4(bx + c * BX_LEN + BX_7 + 272, b3 + 1);
                        sts4(bx + c * BX_LEN + BX_9 + 272, t + 1);
                    }
                }
            };
            auto reload = [&](int c, uint32_t a) { const uint4 v = lds4(a); uw[c][0] = v.x; uw[c][1] = v.y; uw[c][2] = v.z; uw[c][3] = v.w; };
            if (warp >= 6) {
#pragma unroll
                for (int c = 0; c < 3; c++) reload(c, ua - 1024 + (c + 2) * ULEN * 2);
            }
            if (warp >= 4) {
#pragma unroll
                for (int c = 3; c < 5; c++) reload(c, ua - 2048 + c * ULEN * 2);
            }
            box(Int<0>(), Int<3>(), warp < 6 ? tid : tid - 64, warp < 6 ? 0 : 2, warp < 4);
            if (warp >= 4) box(Int<3>(), Int<5>(), tid - 128, 0, true);
            else if (tid >= 128 - CV_CPB) {
                const int c = 127 - tid;
                const uint2 v = *reinterpret_cast<const uint2*>(Us + c * ULEN + UPADF);
                const float s1 = __uint_as_float(v.x << 16), s2 = s1 + __uint_as_float(v.x & 0xffff0000u), s3 = s2 + __uint_as_float(v.y << 16), s4 = s3 + __uint_as_float(v.y & 0xffff0000u);
                unsigned char* bc = sm + CV_SM_B + c * BX_LEN;
                *reinterpret_cast<uint32_t*>(bc + BX_5 + 156) = pack2(s1, s2);
                *reinterpret_cast<uint2*>(bc + BX_7 + 264) = make_uint2(v.x << 16, pack2(s2, s3));
                *reinterpret_cast<uint2*>(bc + BX_9 + 264) = make_uint2(pack2(s1, s2), pack2(s3, s4));
            }
        }
        __syncwarp();
        if (lane == 0) mbar_arrive(cnt + 40);
        TSTAMP(2); CST(2);
        if (layer && blockIdx.x == 0 && tid == 224) g_epoch = ld_epoch();
        __syncwarp();
        if ((0x6e >> warp) & 1) {
            constexpr int seq[16] = {0, 1, 2, 3, 4, 5, 6, 32, 7, 8, 9, 33, 10, 34, 11, 12};
            uint2 f[20];
            mbar_wait(cnt, 0);
            const uint32_t e8 = lc.e4 + 428 - (lane & 28);
#pragma unroll
            for (int k = 0; k < 13; k++) f[k] = make_uint2(lds1(k < 10 ? lc.e4 + 32 * k + 16 : e8 + 32 * k - 304), lds1(k < 10 ? lc.e4 + 32 * k : e8 + 32 * k - 320));
            f[19] = make_uint2(lds1(lc.en), lds1(lc.en - 32));
            far(Int<4>(), seq, lc, tc, lane, f, lds1(smem_u32(sm + CV_SM_T) + TAPB * tc + TAPE + 1672));
        }
    }
    {
        CV_IDX
        if ((0xc91 >> warp) & 1) {
            const int c = __popc(0xc91 & ((1 << warp) - 1));
            uint4 xv[2], yv[2];
#pragma unroll
            for (int k = 0; k < 2; k++) xv[k] = ldx(smem_u32(Xs + c * XLEN) + 512 * k + (lane >> 4) * 256 + (lane & 15) * 8);
            const uint32_t u0 = lds1(smem_u32(Us + c * ULEN) + (lane == 31 ? UPADF * 2 : 0));
            mbar_wait(cnt + 8 * c, 0);
#pragma unroll
            for (int k = 0; k < 2; k++) yv[k] = lds4(smem_u32(sm + CV_SM_Y) + c * 8192 + 512 * k + usw(lane) * 16);
            const uint4 yz = lds4(smem_u32(sm + CV_SM_Y) + c * 8192 + 4096 + usw(lane) * 16);
            const float kk = __uint_as_float(lds1(smem_u32(sm + CV_SM_T) + TAPB * c + TAPE + 1272) << 16);
            yv[1].x = add2(yv[1].x, yz.x); yv[1].y = add2(yv[1].y, yz.y); yv[1].z = add2(yv[1].z, yz.z);
            yv[1].w = pack2(fmaf(kk, __uint_as_float(u0 << 16), __uint_as_float(yv[1].w << 16) + __uint_as_float(yz.w << 16)),
                            fmaf(kk, __uint_as_float(u0 << 16) + __uint_as_float(u0 & 0xffff0000u), __uint_as_float(yv[1].w & 0xffff0000u) + __uint_as_float(yz.w & 0xffff0000u)));
#pragma unroll
            for (int k = 0; k < 2; k++) cv_store(dq + c * XCP * 2 + (lane >> 4) * 256 + (lane & 15) * 8 + 512 * k, xv[k], yv[k]);
        }
        TSTAMP(4); CST(8);
        if (layer == 1) {
            const int rb = (blockIdx.x >> 3) + (warp & 8) * 2, cg = blockIdx.x & 7, ch = (tid >> 3) & 31;
            const bf16* src = dst + (size_t)(cg * 80 + ch) * XCP + rb * 64 + (tid & 7) * 8;
            uint32_t v[3][4];
            __syncthreads();
            if (warp & 8) { const uint32_t c0 = clock(); while (clock() - c0 < 300) ; }
            uint32_t todo = (warp & 4) ? 3 : 7;
#pragma unroll 1
            for (int it = 0; it < SPIN_MAX; it++) {
#pragma unroll
                for (int k = 0; k < 3; k++)
                    if (todo >> k & 1)
                        asm volatile("ld.relaxed.gpu.global.v4.u32 {%0,%1,%2,%3}, [%4];" : "=r"(v[k][0]), "=r"(v[k][1]), "=r"(v[k][2]), "=r"(v[k][3]) : "l"(src + k * (32 * XCP)) : "memory");
#pragma unroll
                for (int k = 0; k < 3; k++)
                    if ((todo >> k & 1) && v[k][0] != ~0u && v[k][1] != ~0u && v[k][2] != ~0u && v[k][3] != ~0u) {
                        *reinterpret_cast<uint4*>(sm + (32 * k + ch) * 272 + ((tid & 7) + (warp & 8)) * 16) = make_uint4(v[k][0], v[k][1], v[k][2], v[k][3]);
                        todo ^= 1u << k;
                    }
                if (!todo) break;
                __nanosleep(CV_SLEEP);
            }
            __syncwarp();
            asm volatile("bar.sync %0, 256;" ::"r"(warp & 8) : "memory");
            uint32_t w[12];
#pragma unroll
            for (int k = 0; k < 3; k++) ldsm_x4(&w[4 * k], smem_u32(sm) + min(32 * k + lane, 79) * 272 + warp * 16);
            const uint32_t ot = smem_u32(sm + CV_SM_O) + warp * 1280, oa = ot + (lane & 7) * 160 + (lane >> 3) * 16;
            stsm_x4_t(oa, w[0], w[1], w[2], w[3]);
            stsm_x4_t(oa + 64, w[4], w[5], w[6], w[7]);
            asm volatile("stmatrix.sync.aligned.m8n8.x2.trans.shared.b16 [%0], {%1,%2};" ::"r"(oa + 128), "r"(w[8]), "r"(w[9]) : "memory");
            fence_async_smem();
            __syncwarp();
            if (lane == 0) {
                asm volatile("cp.async.bulk.tensor.3d.global.shared::cta.bulk_group [%0, {%1, %2, %3}], [%4];" ::"l"(&tmOut), "r"(cg * 80), "r"((rb >> 1) * 64 + 8 * (warp & 7)), "r"(rb & 1), "r"(ot) : "memory");
                asm volatile("cp.async.bulk.commit_group;" ::: "memory");
                asm volatile("cp.async.bulk.wait_group.read 0;" ::: "memory");
            }
        }
    }
    TSTAMP(3); CST(9); CST_END;
    GSTAMP(g_tim, 14);
    SPAN(3 + 4 * layer, 3);
}

template <int TA, int TB>
__device__ __forceinline__ void wgmma_n240(float (&d)[120], uint64_t da, uint64_t db, int acc) {
    asm volatile("{\n.reg .pred p;\nsetp.ne.b32 p, %124, 0;\nwgmma.mma_async.sync.aligned.m64n240k16.f32.bf16.bf16 {%0,%1,%2,%3,%4,%5,%6,%7,%8,%9,%10,%11,%12,%13,%14,%15,%16,%17,%18,%19,%20,%21,%22,%23,%24,%25,%26,%27,%28,%29,%30,%31,%32,%33,%34,%35,%36,%37,%38,%39,%40,%41,%42,%43,%44,%45,%46,%47,%48,%49,%50,%51,%52,%53,%54,%55,%56,%57,%58,%59,%60,%61,%62,%63,%64,%65,%66,%67,%68,%69,%70,%71,%72,%73,%74,%75,%76,%77,%78,%79,%80,%81,%82,%83,%84,%85,%86,%87,%88,%89,%90,%91,%92,%93,%94,%95,%96,%97,%98,%99,%100,%101,%102,%103,%104,%105,%106,%107,%108,%109,%110,%111,%112,%113,%114,%115,%116,%117,%118,%119}, %120, %121, p, 1, 1, %122, %123;\n}"
                 : "+f"(d[0]), "+f"(d[1]), "+f"(d[2]), "+f"(d[3]), "+f"(d[4]), "+f"(d[5]), "+f"(d[6]), "+f"(d[7]), "+f"(d[8]), "+f"(d[9]), "+f"(d[10]), "+f"(d[11]), "+f"(d[12]), "+f"(d[13]), "+f"(d[14]), "+f"(d[15]), "+f"(d[16]), "+f"(d[17]), "+f"(d[18]), "+f"(d[19]), "+f"(d[20]), "+f"(d[21]), "+f"(d[22]), "+f"(d[23]), "+f"(d[24]), "+f"(d[25]), "+f"(d[26]), "+f"(d[27]), "+f"(d[28]), "+f"(d[29]), "+f"(d[30]), "+f"(d[31]), "+f"(d[32]), "+f"(d[33]), "+f"(d[34]), "+f"(d[35]), "+f"(d[36]), "+f"(d[37]), "+f"(d[38]), "+f"(d[39]), "+f"(d[40]), "+f"(d[41]), "+f"(d[42]), "+f"(d[43]), "+f"(d[44]), "+f"(d[45]), "+f"(d[46]), "+f"(d[47]), "+f"(d[48]), "+f"(d[49]), "+f"(d[50]), "+f"(d[51]), "+f"(d[52]), "+f"(d[53]), "+f"(d[54]), "+f"(d[55]), "+f"(d[56]), "+f"(d[57]), "+f"(d[58]), "+f"(d[59]), "+f"(d[60]), "+f"(d[61]), "+f"(d[62]), "+f"(d[63]), "+f"(d[64]), "+f"(d[65]), "+f"(d[66]), "+f"(d[67]), "+f"(d[68]), "+f"(d[69]), "+f"(d[70]), "+f"(d[71]), "+f"(d[72]), "+f"(d[73]), "+f"(d[74]), "+f"(d[75]), "+f"(d[76]), "+f"(d[77]), "+f"(d[78]), "+f"(d[79]), "+f"(d[80]), "+f"(d[81]), "+f"(d[82]), "+f"(d[83]), "+f"(d[84]), "+f"(d[85]), "+f"(d[86]), "+f"(d[87]), "+f"(d[88]), "+f"(d[89]), "+f"(d[90]), "+f"(d[91]), "+f"(d[92]), "+f"(d[93]), "+f"(d[94]), "+f"(d[95]), "+f"(d[96]), "+f"(d[97]), "+f"(d[98]), "+f"(d[99]), "+f"(d[100]), "+f"(d[101]), "+f"(d[102]), "+f"(d[103]), "+f"(d[104]), "+f"(d[105]), "+f"(d[106]), "+f"(d[107]), "+f"(d[108]), "+f"(d[109]), "+f"(d[110]), "+f"(d[111]), "+f"(d[112]), "+f"(d[113]), "+f"(d[114]), "+f"(d[115]), "+f"(d[116]), "+f"(d[117]), "+f"(d[118]), "+f"(d[119])
                 : "l"(da), "l"(db), "n"(TA), "n"(TB), "r"(acc));
}

__device__ __forceinline__ void wgmma_n80(float (&d)[40], uint64_t da, uint64_t db, int acc) {
    asm volatile("{\n.reg .pred p;\nsetp.ne.b32 p, %42, 0;\nwgmma.mma_async.sync.aligned.m64n80k16.f32.bf16.bf16 {%0,%1,%2,%3,%4,%5,%6,%7,%8,%9,%10,%11,%12,%13,%14,%15,%16,%17,%18,%19,%20,%21,%22,%23,%24,%25,%26,%27,%28,%29,%30,%31,%32,%33,%34,%35,%36,%37,%38,%39}, %40, %41, p, 1, 1, 0, 1;\n}"
                 : "+f"(d[0]), "+f"(d[1]), "+f"(d[2]), "+f"(d[3]), "+f"(d[4]), "+f"(d[5]), "+f"(d[6]), "+f"(d[7]), "+f"(d[8]), "+f"(d[9]), "+f"(d[10]), "+f"(d[11]), "+f"(d[12]), "+f"(d[13]), "+f"(d[14]), "+f"(d[15]), "+f"(d[16]), "+f"(d[17]), "+f"(d[18]), "+f"(d[19]), "+f"(d[20]), "+f"(d[21]), "+f"(d[22]), "+f"(d[23]), "+f"(d[24]), "+f"(d[25]), "+f"(d[26]), "+f"(d[27]), "+f"(d[28]), "+f"(d[29]), "+f"(d[30]), "+f"(d[31]), "+f"(d[32]), "+f"(d[33]), "+f"(d[34]), "+f"(d[35]), "+f"(d[36]), "+f"(d[37]), "+f"(d[38]), "+f"(d[39])
                 : "l"(da), "l"(db), "r"(acc));
}

constexpr int A1_THREADS = 384;
constexpr int A1_NST = 4;
#define A1_SKEW 8
constexpr int A1_STAGE = 16384 + WQ_STAGE;
constexpr int A1_KVP = 336;
constexpr int A1_SM_KV = 2 * A1_STAGE;
constexpr int A1_SM_BAR = A1_NST * A1_STAGE;
constexpr int A1_SM_RS = A1_SM_BAR + 512;
constexpr int A1_SM_W0 = A1_SM_BAR + 3072, A1_SM_W3 = A1_SM_BAR - 3 * WOB, A1_SM_A1 = 2 * WOB, A1_SM_A0 = A1_SM_A1 + 61440;
constexpr int A1_SM_XA = A1_SM_W0 + 2 * WOB, A1_SM_XB = A1_SM_XA + 2048;
constexpr int A1_SMEM = A1_SM_W0 + 3 * WOB + CST_EXTRA;
static_assert(A1_SM_W3 >= A1_SM_KV + 144 * A1_KVP && A1_SM_W3 % 512 == 0 && A1_SM_A1 % 1024 == 0 && A1_SM_A0 <= A1_SM_KV && A1_SM_A0 + 61440 <= A1_SM_W3 && A1_SMEM <= 232448, "layout");
__device__ __forceinline__ constexpr uint32_t wo_off(int h) { return h * WOB + (h < 3 ? A1_SM_W0 : h < 6 ? A1_SM_W3 - 3 * WOB : -6 * WOB); }
#define A1_FRED "red.relaxed.gpu.global.add.u32"
#define A1_FLD "ld.acquire.gpu.global.u32"
#define ST_SLEEP 20
#define ST_SLEEP0 300
#define WO_LATE bar_done
#define A1_P0 2
#define A1_PW (kb - 2)
#define A1_FSPIN SPIN_MAX
#define A1_FSLEEP 40
#define YT_LAYER 1
#define WOT 352
#define A1_WOAT 6

template <int L>
__device__ __forceinline__ void a1_mainloop(float (&acc)[120], uint32_t sbase, uint32_t bars, int wg, int tile) {
    constexpr int layer = L; (void)layer;
    const uint64_t da0 = L ? make_desc(sbase + wg * 8192, 8192, 1024, 1) : make_desc(sbase + wg * 8192, 16, 1024, 1), db0 = make_desc(sbase + 16384, 1024, 256, 3);
#pragma unroll 1
    for (int t = 0;; t++) {
        const int st = t % A1_NST;
        mbar_wait(bars + 8 * st, (t / A1_NST) & 1);
        if (t == A1_SKEW && wg == 0) mbar_wait(bars + 160, 0);
        TSTAMP3(1 + t);
        if (t == 0) CSA(0);
        wgmma_fence();
#pragma unroll
        for (int kk = 0; kk < 4; kk++) wgmma_n240<L, 1>(acc, da0 + (uint32_t)(st * (A1_STAGE / 16) + kk * (L ? 128 : 2)), db0 + (uint32_t)(st * (A1_STAGE / 16) + (kk >> 1) * (WQ_STAGE / 32) + (kk & 1) * 32), kk ? 1 : t);
        wgmma_commit();
        if (t == 9) break;
        if (t == A1_SKEW - 1 && wg == 0) wgmma_wait<0>(); else wgmma_wait<1>();
        if (t > 0 && (threadIdx.x & 127) == 0) {
            if (t != A1_SKEW || wg) mbar_arrive(bars + 8 * (A1_NST + (t - 1) % A1_NST));
            if (t == A1_SKEW - 1 && wg == 0) mbar_arrive(bars + 8 * (A1_NST + t % A1_NST));
        }
    }
}

template <bool MAP>
__global__ void __launch_bounds__(A1_THREADS, 1) a1_kernel(const int layer, const bf16* __restrict__ x0, const unsigned char* __restrict__ wo,
                                                           float2* __restrict__ rsum, uint4* __restrict__ of, const __grid_constant__ CUtensorMap tmX,
                                                           const __grid_constant__ CUtensorMap tmR, const __grid_constant__ CUtensorMap tmX1, const __grid_constant__ TileTab tab) {
    extern __shared__ __align__(1024) unsigned char stg[];
    const uint32_t sbase = smem_u32(stg);
    const uint32_t bars = sbase + A1_SM_BAR;
    const uint32_t bar_stat = bars + 64, bar_kv = bars + 72, bar_rd = bars + 168;
    const uint32_t bar_wo = bars + 208, bar_done = bars + 216, bar_pv = bars + 224, bar_kvf = bars + 232, bar_f2 = bars + 248, bar_e2 = bars + 384, que = bars + 448;
    const int tid = threadIdx.x;
    const int w = __shfl_sync(~0u, tid >> 5, 0), wg = w >> 2;
    uint32_t smid;
    asm volatile("mov.u32 %0, %smid;" : "=r"(smid));
    const uint4 tv = tab.e[(MAP ? smid : blockIdx.x) + (tid & (smid >> 12))];
    const bool one = elect();
    if (w == 8) {
        if (one) {
            prefetch_tmap(&tmX);
#pragma unroll
            for (int i = 0; i < A1_NST; i++) mbar_init(bars + 8 * i, 1);
            asm volatile("fence.mbarrier_init.release.cluster;" ::: "memory");
        }
        __syncwarp();
        asm volatile("bar.arrive 0, 384;" ::: "memory");
    }
    const uint32_t tz = __shfl_sync(~0u, tv.z, 0);
    const int tile = tz >> 24, mb = tz & 15, hg = (tz >> 8) & 7;
    struct { const unsigned char* wq; int kb0, layer; } te = {(const unsigned char*)(((uint64_t)__shfl_sync(~0u, tv.y, 0) << 32) | __shfl_sync(~0u, tv.x, 0)), (int)(tz >> 16) & 7, (int)tz & 16};
    float2* rst = reinterpret_cast<float2*>(stg + A1_SM_RS) + 8;
    auto issue_w = [&](int it) { bulk_load(sbase + (it % A1_NST) * A1_STAGE + 16384, te.wq + it * WQ_STAGE, WQ_STAGE, bars + 8 * (it % A1_NST)); };
    auto issue_x = [&](int it, int kb) {
        asm volatile("cp.async.bulk.tensor.5d.shared::cluster.global.mbarrier::complete_tx::bytes [%0], [%1, {%3, %3, %3, %4, %5}], [%2];"
                     ::"r"(sbase + (it % A1_NST) * A1_STAGE), "l"(&tmX), "r"(bars + 8 * (it % A1_NST)), "r"(0), "r"(mb), "r"(kb) : "memory");
    };
    if (w == 8 && tile < 128) {
        if (one) {
#define PW asm volatile("griddepcontrol.wait;" ::: "memory");
            if (te.layer) { issue_w(0); PW issue_x(0, te.kb0); issue_x(1, te.kb0 + 1); }
            else { issue_x(0, te.kb0); issue_x(1, te.kb0 + 1); PW issue_w(0); }
            issue_w(1);
#pragma unroll
            for (int i = 0; i < A1_NST; i++) mbar_expect_tx(bars + 8 * i, A1_STAGE);
            asm volatile("griddepcontrol.launch_dependents;" ::: "memory");
#pragma unroll
            for (int kb = 2; kb < A1_P0; kb++) { issue_x(kb, te.kb0 + kb); issue_w(kb); }
            DBGC(34); DBGV(33, smid); DBGV(40, t_entry); DBGV(30, t_a); DBGV(31, t_b); DBGV(32, t_c); DBGV(38, t_d); DBGV(39, t_e);
        }
    }
    if (tile >= 128) { sm_idle(layer); return; }
    if (wg == 2) {
        if (w != 8) {
            if (tid == 320) {
                prefetch_tmap(&tmR); prefetch_tmap(&tmX1);
                uint32_t ns;
                asm volatile("mov.u32 %0, %nsmid;" : "=r"(ns));
                if (MAP && ns != 132) __trap();
            }
            if (w == 11 && layer == 0 && elect()) {
                mbar_init(bars + 240, 1);
                asm volatile("fence.mbarrier_init.release.cluster;" ::: "memory");
                mbar_expect_tx(bars + 240, 20480);
                bulk_load(sbase + A1_SM_W0, x0 + (size_t)(mb * 128 + hg * 16) * DM, 20480, bars + 240);
            }
            __syncwarp();
            asm volatile("bar.sync 0, 384;" ::: "memory");
        }
        if (w == 9) {
            asm volatile("bar.arrive 3, 64;" ::: "memory");
            if (layer == 0) pdl_sync();
            float4 a[2] = {};
#pragma unroll
            for (int k = 0; k < 10; k++)
#pragma unroll
                for (int h = 0; h < 2; h++) {
                    const int c4 = min(tid - 288 + 32 * h, 59);
                    const float4 v = __ldcg(reinterpret_cast<const float4*>(g_csp + k * 1920 + hg * 80) + c4 + (c4 / 20) * 140);
                    a[h].x += v.x; a[h].y += v.y; a[h].z += v.z; a[h].w += v.w;
                }
#pragma unroll
            for (int h = 0; h < 2; h++)
#pragma unroll
                for (int k = 0; k < 4; k++) {
                    const float c = 0.5f * (k == 0 ? a[h].x : k == 1 ? a[h].y : k == 2 ? a[h].z : a[h].w), c1 = c - rbf(c), c2 = c1 - rbf(c1);
                    *reinterpret_cast<uint4*>(stg + A1_SM_XB + (4 * min(tid - 288 + 32 * h, 59) + k) * 16) = make_uint4(pack2(c, c1), pack2(c2, 0.f), 0u, 0u);
                }
            fence_async_smem();
            __syncwarp();
            if (tid == 288) mbar_arrive(bar_stat);
            CSA(1);
            uint4* pre = of + (mb * 8 + hg) * 1280 + (tid - 288);
#pragma unroll 1
            for (int k = 0; k < 5 + 5 * layer; k++) {
#pragma unroll
                for (int i = 0; i < 8; i++) asm volatile("st.global.v4.u32 [%0], {%1,%1,%1,%1};" ::"l"(pre + 32 * i), "r"(~0u) : "memory");
                pre += k < 5 ? 256 : XCP / 8;
                if (k == 4) {
                    CSA(2);
                    asm volatile("fence.acq_rel.gpu;" ::: "memory");
                    asm volatile("fence.proxy.async.global;" ::: "memory");
                    __syncwarp();
                    if (tid == 288) mbar_arrive(bar_done);
                    CSA(3);
                    pre = reinterpret_cast<uint4*>(g_yT) + tile * (5 * XCP / 8) + (tid - 288);
                }
            }
            TSTAMP1T(9, 288);
        } else if (w == 8) {
            asm volatile("bar.sync 3, 64;" ::: "memory");
            if (elect()) {
#pragma unroll 1
                for (int kb = A1_P0; kb < 10; kb++) {
                    if (kb < A1_NST) mbar_wait(bars + 8 * A1_PW, 0);
                    else {
                        mbar_wait(bars + 8 * (A1_NST + kb % A1_NST), ((kb / A1_NST) - 1) & 1);
                        if (layer && kb < 9) mbar_wait(bar_rd + 8 * (kb - A1_NST), 0);
                        mbar_expect_tx(bars + 8 * (kb % A1_NST), A1_STAGE);
                    }
                    issue_x(kb, kb < 5 ? kb + te.kb0 : kb - te.kb0); issue_w(kb);
                    if (kb == (layer ? A1_WOAT : 9)) {
                        if (!layer) mbar_wait(bar_rd + 32, 0);
                        mbar_expect_tx(bar_wo, 8 * WOB);
                        bulk_load(sbase + A1_SM_W0, wo + hg * 8 * WOB, 2 * WOB, bar_wo);
                    }
                }
                TSTAMP1T(6, 256);
                mbar_wait(bars + 8 * (A1_NST + 3), 1);
                bulk_load(sbase + A1_SM_W3, wo + (hg * 8 + 3) * WOB, 3 * WOB, bar_wo);
            }
            __syncwarp();
        } else {
            const int j = tid - 320;
            const uint32_t tag = ld_epoch();
            if (tid == 352) sm_started(layer);
            const int ch = j & 7, kg = (j >> 3) & 3;
            const unsigned char* src = stg + (layer ? (j >> 5) * 8192 + (hg & 3) * 2048 : A1_SM_W0 + (j >> 2) * 1280);
            const int of0 = layer ? kg * 128 + ((ch ^ kg) << 4) : (j & 7) << 4, ofx = layer ? 576 : 64, ofy = layer ? 1024 : 128;
            float s[8], q[8], p0[8];
#pragma unroll
            for (int i = 0; i < 8; i++) { s[i] = 0.f; q[i] = 0.f; }
#pragma unroll 1
            for (int it = 0; it < 5; it++) {
                uint4 v[4];
                mbar_wait(layer ? bars + 8 * (it % A1_NST) : bars + 240, layer * it / A1_NST);
#pragma unroll
                for (int k = 0; k < 4; k++) v[k] = *reinterpret_cast<const uint4*>(src + (layer ? (it % A1_NST) * A1_STAGE : it * 256) + (k & 1 ? of0 ^ ofx : of0) + (k >> 1) * ofy);
                if (it == 0) {
                    const uint4 pv = *reinterpret_cast<const uint4*>(src + (layer ? ch << 4 : 0));
                    const uint32_t w[4] = {pv.x, pv.y, pv.z, pv.w};
#pragma unroll
                    for (int i = 0; i < 4; i++) { p0[2 * i] = __uint_as_float((layer ? w[i] : w[0]) << 16); p0[2 * i + 1] = __uint_as_float(layer ? w[i] & 0xffff0000u : w[0] << 16); }
                }
                asm volatile("" :: "r"(v[0].x), "r"(v[1].x), "r"(v[2].x), "r"(v[3].x), "f"(p0[0]) : "memory");
                __syncwarp();
                if ((tid & 31) == 0) mbar_arrive(bar_rd + 8 * it);
#pragma unroll
                for (int k = 0; k < 4; k++) {
                    const uint32_t w[4] = {v[k].x, v[k].y, v[k].z, v[k].w};
#pragma unroll
                    for (int i = 0; i < 4; i++) {
                        const float a = __uint_as_float(w[i] << 16) - p0[2 * i], b = __uint_as_float(w[i] & 0xffff0000u) - p0[2 * i + 1];
                        s[2 * i] += a; s[2 * i + 1] += b; q[2 * i] = fmaf(a, a, q[2 * i]); q[2 * i + 1] = fmaf(b, b, q[2 * i + 1]);
                    }
                }
            }
            float o[4];
            int row;
            if (layer == 0) {
                float s0 = ((s[0] + s[1]) + (s[2] + s[3])) + ((s[4] + s[5]) + (s[6] + s[7])), q0 = ((q[0] + q[1]) + (q[2] + q[3])) + ((q[4] + q[5]) + (q[6] + q[7]));
#pragma unroll
                for (int o = 1; o <= 2; o <<= 1) { s0 += __shfl_xor_sync(~0u, s0, o); q0 += __shfl_xor_sync(~0u, q0, o); }
                if ((j & 3) == 0) {
                    const float d = s0 * (1.0f / DM);
                    const uint32_t ms = pack2(p0[0] + d, sqrt_apx(rbf(rbf(fmaxf(fmaf(-d, d, q0 * (1.0f / DM)), 0.f)) + 1e-5f)));
                    asm volatile("st.global.cg.u64 [%0], %1;" ::"l"(g_rstat + mb * 128 + (j & 4) * 16 + hg * 8 + (j >> 3)), "l"(tagw(ms, tag)) : "memory");
                    g_piv[mb * 128 + hg * 16 + ((j >> 2) & 8) + (j & 4) + ((j >> 3) & 3)] = __ushort_as_bfloat16((unsigned short)ms);
                }
                ulonglong2 v;
#pragma unroll 1
                for (int it = 0; it < SPIN_MAX; it++) {
                    v = ld_tag2(reinterpret_cast<const ulonglong2*>(g_rstat + mb * 128) + j);
                    if (tag_ok(v, tag)) break;
                    __nanosleep(100);
                }
                o[0] = __uint_as_float((uint32_t)v.x << 16); o[1] = rcp_apx(__uint_as_float((uint32_t)v.x & 0xffff0000u));
                o[2] = __uint_as_float((uint32_t)v.y << 16); o[3] = rcp_apx(__uint_as_float((uint32_t)v.y & 0xffff0000u));
                row = 2 * j;
            } else {
#pragma unroll
                for (int i = 0; i < 4; i++) {
                    const bool up = kg & 2;
                    const float ss = __shfl_xor_sync(~0u, up ? s[i] : s[i + 4], 16), qq = __shfl_xor_sync(~0u, up ? q[i] : q[i + 4], 16);
                    s[i] = (up ? s[i + 4] : s[i]) + ss; q[i] = (up ? q[i + 4] : q[i]) + qq; p0[i] = up ? p0[i + 4] : p0[i];
                }
#pragma unroll
                for (int i = 0; i < 2; i++) {
                    const bool up = kg & 1;
                    const float ss = __shfl_xor_sync(~0u, up ? s[i] : s[i + 2], 8), qq = __shfl_xor_sync(~0u, up ? q[i] : q[i + 2], 8);
                    s[i] = (up ? s[i + 2] : s[i]) + ss; q[i] = (up ? q[i + 2] : q[i]) + qq; p0[i] = up ? p0[i + 2] : p0[i];
                }
                uint4* gp = g_halo + 86016 + mb * 512 + j;
                const float d0 = s[0] * (1.0f / 80.0f), d1 = s[1] * (1.0f / 80.0f);
                asm volatile("st.relaxed.gpu.global.v4.f32 [%0], {%1,%2,%3,%4};" ::"l"(gp + hg * 64), "f"(p0[0] + d0), "f"(fmaxf(fmaf(-d0, s[0], q[0]), 0.f)), "f"(p0[1] + d1), "f"(fmaxf(fmaf(-d1, s[1], q[1]), 0.f)) : "memory");
                __nanosleep(ST_SLEEP0);
                uint32_t pw[8][4], todo = 0xff;
#pragma unroll 1
                for (int it = 0; it < SPIN_MAX; it++) {
#pragma unroll
                    for (int k = 0; k < 8; k++)
                        if (todo >> k & 1) asm volatile("ld.relaxed.gpu.global.v4.u32 {%0,%1,%2,%3}, [%4];" : "=r"(pw[k][0]), "=r"(pw[k][1]), "=r"(pw[k][2]), "=r"(pw[k][3]) : "l"(gp + k * 64) : "memory");
#pragma unroll
                    for (int k = 0; k < 8; k++)
                        if (__all_sync(~0u, pw[k][0] != ~0u && pw[k][1] != ~0u && pw[k][2] != ~0u && pw[k][3] != ~0u)) todo &= ~(1u << k);
                    if (!todo) break;
                    __nanosleep(ST_SLEEP);
                }
#pragma unroll
                for (int r = 0; r < 2; r++) {
                    float mean = 0.f, m2 = 0.f;
#pragma unroll
                    for (int k = 0; k < 8; k++) mean += __uint_as_float(pw[k][2 * r]);
                    mean *= 0.125f;
#pragma unroll
                    for (int k = 0; k < 8; k++) {
                        const float dm = __uint_as_float(pw[k][2 * r]) - mean;
                        m2 += fmaf(80.0f * dm, dm, __uint_as_float(pw[k][2 * r + 1]));
                    }
                    o[2 * r] = rbf(mean);
                    o[2 * r + 1] = rcp_apx(rbf(sqrt_apx(rbf(rbf(m2 * (1.0f / DM)) + 1e-5f))));
                }
                row = (j >> 5) * 64 + (j & 7) * 8 + ((j >> 3) & 3) * 2;
                if (hg == 0) *reinterpret_cast<uint32_t*>(g_piv + SEQ + mb * 128 + 2 * (row & 60) + 4 * (row >> 6) + (row & 3)) = __byte_perm(__float_as_uint(o[0]), __float_as_uint(o[2]), 0x7632);
            }
#pragma unroll
            for (int r = 0; r < 2; r++)
                *reinterpret_cast<uint4*>(stg + A1_SM_XA + (row + r) * 16) = make_uint4(__byte_perm(__float_as_uint(-o[2 * r]), 0, 0x3232), __float_as_uint(-o[2 * r]) >> 16, 0u, 0u);
            *reinterpret_cast<float4*>(rst + row + (row >> 6) * 8) = make_float4(o[0], o[1], o[2], o[3]);
            fence_async_smem();
            TSTAMP1T(7, 320); CSA(1);
            if (tid == 320) DBGC(44);
            __syncwarp();
            if ((tid & 31) == 0) mbar_arrive(bar_stat);
        }
        CSA(4); CSA_END;
        if (tid == 320) DBGCAL(0);
        if (tid == WOT) {
            mbar_wait(WO_LATE, 0);
            mbar_wait(bar_done, 0);
            bulk_load(sbase, wo + (hg * 8 + 6) * WOB, 2 * WOB, bar_wo);
            bulk_load(sbase + A1_SM_W0 + 2 * WOB, wo + (hg * 8 + 2) * WOB, WOB, bar_wo);
        }
        __syncwarp();
#define FWA 11
#define FWB 10
        if (w == FWA || w == FWB) {
            const int cw = w == FWB;
            const uint32_t* fl = reinterpret_cast<const uint32_t*>(rsum + 2 * SEQ) + (((layer * 16 + mb) * 2 + cw) * 8 + (tid & 7)) * FSTR;
            const unsigned char* src = reinterpret_cast<const unsigned char*>(of) + mb * 163840 + cw * 10240 + (tid & 7) * 20480;
            const uint32_t sl = sbase + (cw ? A1_SM_A1 : A1_SM_A0);
            mbar_wait(cw ? bar_done : bar_kvf, 0);
            if ((tid & 31) == 0) {
                mbar_expect_tx(bar_f2 + 64 * cw + 64, 10240);
                tma_load_3d(sl + 51200, &tmR, layer ? 0 : hg * 80, layer ? hg * 80 : mb * 64, layer ? mb * 2 + cw : cw, bar_f2 + 64 * cw + 64);
            }
            __syncwarp();
            uint32_t pend = 0xffu & ~(1u << hg), v = 0;
            const uint32_t bo = wo_off((tid & 7) + ((tid & 7) < hg)) >> 4, lt = (1u << (tid & 31)) - 1;
#pragma unroll 1
            for (int it = 0; pend && it < 2 * SPIN_MAX; it++) {
                if (v != 4 && (pend >> (tid & 31) & 1)) asm volatile(A1_FLD " %0, [%1];" : "=r"(v) : "l"(fl) : "memory");
                uint32_t fr;
                asm volatile("{\n.reg .pred p;\nmbarrier.test_wait.parity.shared::cta.b64 p, [%1], 0;\nselp.b32 %0, 1, 0, p;\n}" : "=r"(fr) : "r"(bar_e2 + 16 * cw + (tid & 1) * 8) : "memory");
                fr = __ballot_sync(~0u, fr);
                uint32_t m = __ballot_sync(~0u, v == 4 || it >= A1_FSPIN) & pend;
                const int q = 8 - __popc(pend) + __popc(m & lt);
                m &= __ballot_sync(~0u, q < ((fr & 2) ? 8 : (fr & 1) ? 7 : 5));
                pend ^= m;
                if (m >> (tid & 31) & 1) DBGC(12 + cw * 8 + (tid & 7));
                if (!m) __nanosleep(A1_FSLEEP);
                else asm volatile("fence.proxy.async.global;" ::: "memory");
                if (m >> (tid & 31) & 1) {
                    bulk_load(q == 7 && !cw ? sbase + A1_SM_W0 : sl + (q < 6 ? q : q - 6) * 10240, src, 10240, bar_f2 + 64 * cw + 8 * q);
                    asm volatile("st.shared.u32 [%0], %1;" ::"r"(que + 32 * cw + 4 * q), "r"(bo) : "memory");
                    mbar_expect_tx(bar_f2 + 64 * cw + 8 * q, 10240);
                    DBGC(44 + cw * 8 + q);
                }
                __syncwarp();
            }
        }
    } else {
        if (one) {
#pragma unroll 1
            for (uint32_t c = tab.cnt[w], b = bars + 56 * w; c; c >>= 4, b += 8)
                if (c & 15) mbar_init(b, c & 15);
            asm volatile("fence.mbarrier_init.release.cluster;" ::: "memory");
        }
        __syncwarp();
        asm volatile("bar.sync 0, 384;" ::: "memory");
        SPAN(1 + 4 * layer, 0);
        constexpr int on = 1;
        float acc[120];
        const int lane = tid & 31, warp = w & 7, g = lane >> 2, t = lane & 3;
        if (on) {
            SPAN(1 + 4 * layer, 1);
            TSTAMP1(0);
            if (threadIdx.x == 0) { GSTAMP(g_tim1, 15); }
            TSTAMP3(0);
            if (tid == 0) TSTAMP2(0);
            TSTAMP4(0);
            if (tid == 0) DBGC(60);
            if (layer == 0) a1_mainloop<0>(acc, sbase, bars, wg, tile); else a1_mainloop<1>(acc, sbase, bars, wg, tile);
            uint32_t ok;
            asm volatile("{\n.reg .pred p;\nmbarrier.test_wait.parity.shared::cta.b64 p, [%1], 0;\nselp.b32 %0, 1, 0, p;\n}" : "=r"(ok) : "r"(bar_stat) : "memory");
            if (tid == 128 && !ok) mbar_arrive(bars + 160);
            __syncwarp();
            mbar_wait(bar_stat, 0);
            wgmma_fence();
            wgmma_n240<0, 0>(acc, make_desc(sbase + A1_SM_XA + wg * 1024, 0, 128, 0), make_desc(sbase + A1_SM_XB, 0, 128, 0), 1);
            wgmma_commit();
            if (tid == 128 && ok) mbar_arrive(bars + 160);
            mbar_wait(bars + 8 * (A1_NST + 3), 1);
        }
        const float2* rw = rst + 16 * warp + 8 * wg;
        const float rb0 = rw[g + 8].y, ra = rw[g].y * 0.22360679774997896f, rb = rb0 * 0.22360679774997896f;
        wgmma_wait<0>();
        if ((tid & 127) == 0) mbar_arrive(bar_done);
        TSTAMP1(2); CSA(1);
        TSTAMP1T(13, 224);
        if ((tid & 127) == 0) DBGC(62 - wg);
        uint32_t f[2][30];
#pragma unroll
        for (int j = 10; j < 30; j++) f[1][j] = pack2(acc[4 * j + 2], acc[4 * j + 3]);
        if ((warp & 3) == 3) {
            uint4* hout = g_halo + (((layer * 16 + mb) * 8 + hg) * 2 + wg) * 168;
#pragma unroll
            for (int j = 0; j < 20; j += 4)
                asm volatile("st.relaxed.gpu.global.v4.u32 [%0], {%1,%2,%3,%4};" ::"l"(hout + 8 * j + lane), "r"(f[1][10 + j]), "r"(f[1][11 + j]), "r"(f[1][12 + j]), "r"(f[1][13 + j]) : "memory");
            if (t == 0) asm volatile("st.relaxed.gpu.global.f32 [%0], %1;" ::"l"(reinterpret_cast<float*>(hout + 160) + g), "f"(rb0) : "memory");
        }
        TSTAMP1T(12, 224);
        const uint32_t kvw = sbase + A1_SM_KV + (16 * warp + 8 * wg) * A1_KVP;
        const uint32_t mrow = kvw + (lane & 7) * A1_KVP + (lane >> 3) * 16;
#pragma unroll
        for (int j = 0; j < 20; j += 4) stsm_x4(mrow + 16 * A1_KVP + 16 * j, f[1][10 + j], f[1][11 + j], f[1][12 + j], f[1][13 + j]);
        __syncwarp();
        if (lane == 0 && (warp & 3) != 3) mbar_arrive(bar_kv + 8 * (warp + 1));
#pragma unroll
        for (int j = 0; j < 30; j++) f[0][j] = pack2(acc[4 * j], acc[4 * j + 1]);
        stsm_x4(mrow + 8 * A1_KVP + 160, f[0][20], f[0][21], f[0][22], f[0][23]);
        stsm_x4(mrow + 8 * A1_KVP + 224, f[0][24], f[0][25], f[0][26], f[0][27]);
        asm volatile("stmatrix.sync.aligned.m8n8.x2.shared.b16 [%0], {%1,%2};" ::"r"(mrow + 8 * A1_KVP + 288), "r"(f[0][28]), "r"(f[0][29]) : "memory");
#pragma unroll
        for (int j = 0; j < 10; j++) f[1][j] = pack2(acc[4 * j + 2], acc[4 * j + 3]);
        __syncwarp();
        uint32_t vb[10][2], vp[12], kp[12];
#pragma unroll
        for (int j = 0; j < 10; j += 2) ldsm_x4_t(&vb[j][0], kvw + (8 + (lane & 15)) * A1_KVP + 160 + (lane >> 4) * 16 + 16 * j);
        const bool up0 = 2 * t > g, up1 = 2 * t + 1 > g, edge = (mb | (warp & 3)) == 0;
        float rk[4];
        auto above = [&]() {
            mbar_wait(bar_kv + 8 * warp, 0);
#pragma unroll
            for (int j = 0; j < 12; j += 4) ldsm_x4(&kp[j], mrow + 16 * j);
            rk[0] = rw[2 * t - (up0 ? 8 : 0)].y; rk[1] = rw[2 * t + 1 - (up1 ? 8 : 0)].y;
#pragma unroll
            for (int j = 0; j < 12; j += 4) ldsm_x4_t(&vp[j], mrow + 160 + 16 * j - (j == 8 ? (lane & 16) * 2 : 0));
            __syncwarp();
            if (lane == 0) mbar_arrive(bar_kvf);
        };
        auto halo = [&]() {
            if (lane == 0) mbar_arrive(bar_kvf);
            const uint4* hin = g_halo + (((layer * 16 + mb - 1) * 8 + hg) * 2 + wg) * 168;
            uint32_t hv[22] = {};
            rk[0] = rw[2 * t].y; rk[1] = rw[2 * t + 1].y;
            if (mb > 0) {
#pragma unroll 1
                for (int it = 0; it < SPIN_MAX; it++) {
#pragma unroll
                    for (int k = 0; k < 20; k += 4)
                        asm volatile("ld.relaxed.gpu.global.v4.u32 {%0,%1,%2,%3}, [%4];" : "=r"(hv[k]), "=r"(hv[k + 1]), "=r"(hv[k + 2]), "=r"(hv[k + 3]) : "l"(hin + 8 * k + lane) : "memory");
                    asm volatile("ld.relaxed.gpu.global.v2.u32 {%0,%1}, [%2];" : "=r"(hv[20]), "=r"(hv[21]) : "l"(reinterpret_cast<const uint2*>(hin + 160) + t) : "memory");
                    uint32_t m = max(hv[20], hv[21]);
#pragma unroll
                    for (int k = 0; k < 20; k += 2) m = __vimax3_u32(m, hv[k], hv[k + 1]);
                    if (!__any_sync(~0u, m == ~0u)) break;
                }
            }
            if (lane == 0) DBGC(52 - 16 * wg);
#pragma unroll
            for (int j = 0; j < 10; j++) {
                kp[j] = hv[j];
                asm volatile("movmatrix.sync.aligned.m8n8.trans.b16 %0, %1;" : "=r"(vp[j]) : "r"(hv[10 + j]));
            }
            if (up0) rk[0] = __uint_as_float(hv[20]);
            if (up1) rk[1] = __uint_as_float(hv[21]);
        };
        rk[2] = rw[2 * t + (up0 ? 0 : 8)].y; rk[3] = rw[2 * t + 1 + (up1 ? 0 : 8)].y;
        uint32_t qs[4][2];
#pragma unroll
        for (int h = 0; h < 4; h++) {
            qs[h][0] = (t >> 1) == (h & 1) ? f[0][5 * (h >> 1) + 2] : 0u; qs[h][1] = (t >> 1) == (h & 1) ? f[1][5 * (h >> 1) + 2] : 0u;
            asm volatile("" : "+r"(qs[h][0]), "+r"(qs[h][1]));
        }
#pragma unroll
        for (int j = 0; j < 10; j++) asm volatile("" : "+r"(f[0][j]), "+r"(f[1][j]), "+r"(f[0][10 + j]));
        if (warp & 3) above(); else if (wg) halo();
        TSTAMP1T(10, 64); CSA(2);
        if (warp && !wg) mbar_wait(bars + 416 + 8 * warp, 0);
        CSA(3);
        float sc[4][3][4];
#pragma unroll
        for (int h = 0; h < 4; h++) {
            const int jb = 5 * (h >> 1) + 3 * (h & 1), js = 5 * (h >> 1) + 2;
#pragma unroll
            for (int nt = 1; nt < 3; nt++) {
#pragma unroll
                for (int e = 0; e < 4; e++) sc[h][nt][e] = 0.f;
                mma_bf16(sc[h][nt], f[0][jb], f[1][jb], f[0][jb + 1], f[1][jb + 1], f[nt - 1][10 + jb], f[nt - 1][11 + jb]);
                mma_bf16_k8(sc[h][nt], qs[h][0], qs[h][1], f[nt - 1][10 + js]);
            }
        }
        if (warp == 0) halo();
        TSTAMP1(8); CSA(4);
#pragma unroll
        for (int h = 0; h < 4; h++) {
            const int jb = 5 * (h >> 1) + 3 * (h & 1), js = 5 * (h >> 1) + 2;
#pragma unroll
            for (int e = 0; e < 4; e++) sc[h][0][e] = 0.f;
            mma_bf16(sc[h][0], f[0][jb], f[1][jb], f[0][jb + 1], f[1][jb + 1], kp[jb], kp[jb + 1]);
            mma_bf16_k8(sc[h][0], qs[h][0], qs[h][1], kp[js]);
        }
        TSTAMP1T(3, 64);
        float p[4][4], sum[4][2];
        uint32_t lg[4][2], mx[4];
        const float rl[4] = {rk[0] * ra, rk[1] * ra, rk[2] * rb, rk[3] * rb};
        auto max2 = [](uint32_t a, uint32_t b) { uint32_t r; asm("max.bf16x2 %0, %1, %2;" : "=r"(r) : "r"(a), "r"(b)); return r; };
#pragma unroll
        for (int h = 0; h < 4; h++) {
            lg[h][0] = pack2((up0 ? sc[h][0][0] : sc[h][1][0]) * rl[0], (up0 ? sc[h][1][2] : sc[h][2][2]) * rl[2]);
            lg[h][1] = pack2((up1 ? sc[h][0][1] : sc[h][1][1]) * rl[1], (up1 ? sc[h][1][3] : sc[h][2][3]) * rl[3]);
            if (edge) {
                if (up0) lg[h][0] = __byte_perm(lg[h][0], 0xce6eu, 0x3254);
                if (up1) lg[h][1] = __byte_perm(lg[h][1], 0xce6eu, 0x3254);
            }
            mx[h] = max2(lg[h][0], lg[h][1]);
        }
#pragma unroll
        for (int o = 1; o <= 2; o <<= 1)
#pragma unroll
            for (int h = 0; h < 4; h++) mx[h] = max2(mx[h], __shfl_xor_sync(~0u, mx[h], o));
#pragma unroll
        for (int h = 0; h < 4; h++)
#pragma unroll
            for (int r = 0; r < 2; r++) {
                const float m = __uint_as_float(r ? mx[h] & 0xffff0000u : mx[h] << 16);
#pragma unroll
                for (int e = 0; e < 2; e++)
                    asm("ex2.approx.ftz.f32 %0, %1;" : "=f"(p[h][2 * r + e]) : "f"((__uint_as_float(r ? lg[h][e] & 0xffff0000u : lg[h][e] << 16) - m) * 1.4426950408889634f));
                sum[h][r] = p[h][2 * r] + p[h][2 * r + 1];
            }
#pragma unroll
        for (int o = 1; o <= 2; o <<= 1)
#pragma unroll
            for (int h = 0; h < 4; h++)
#pragma unroll
                for (int r = 0; r < 2; r++) sum[h][r] += __shfl_xor_sync(~0u, sum[h][r], o);
        TSTAMP1T(5, 64); CSA(5);
        const uint32_t mu = (up0 ? 0xffffu : 0u) | (up1 ? 0xffff0000u : 0u);
        uint32_t ob[10][2];
#pragma unroll
        for (int P = 0; P < 2; P++) {
            float os[2][4];
#pragma unroll
            for (int e = 0; e < 2; e++) {
                const int h = 2 * P + e;
                const float i0 = rcp_apx(sum[h][0]), i1 = rcp_apx(sum[h][1]);
                const uint32_t w0 = pack2(p[h][0] * rk[0] * i0, p[h][1] * rk[1] * i0), w1 = pack2(p[h][2] * rk[2] * i1, p[h][3] * rk[3] * i1);
#pragma unroll
                for (int dt = 0; dt < 3; dt++) {
                    const int j = 5 * P + (dt < 2 ? 3 * e + dt : 2);
                    float o[4] = {0.f, 0.f, 0.f, 0.f};
                    mma_bf16(o, w0 & ~mu, w1 & mu, 0u, w1 & ~mu, vb[j][0], vb[j][1]);
                    mma_bf16_k8(o, w0 & mu, 0u, vp[j]);
                    if (dt < 2) { ob[j][0] = pack2(o[0], o[1]); ob[j][1] = pack2(o[2], o[3]); }
                    else { os[e][0] = o[0]; os[e][1] = o[1]; os[e][2] = o[2]; os[e][3] = o[3]; }
                }
            }
#pragma unroll
            for (int k = 0; k < 4; k++) os[0][k] = t < 2 ? os[0][k] : os[1][k];
            ob[5 * P + 2][0] = pack2(os[0][0], os[0][1]); ob[5 * P + 2][1] = pack2(os[0][2], os[0][3]);
        }
        const uint32_t sl = sbase + (wg ? A1_SM_A1 : A1_SM_A0);
        const uint32_t o0 = (warp & 3) * 2048 + g * 64 + ((t ^ (g >> 1)) << 4), o1 = 8192 + (warp & 3) * 512 + g * 32 + ((t ^ ((g >> 2) << 1)) << 3);
        CSA(15);
        mbar_wait(bar_done, 0);
        if (wg == 0) mbar_wait(bar_kvf, 0);
#pragma unroll
        for (int h = 0; h < 2; h++) {
            asm volatile("st.shared.v4.u32 [%0], {%1,%2,%3,%4};" ::"r"(sl + o0 + h * 1024), "r"(ob[0][h]), "r"(ob[1][h]), "r"(ob[2][h]), "r"(ob[3][h]) : "memory");
            asm volatile("st.shared.v4.u32 [%0], {%1,%2,%3,%4};" ::"r"(sl + o0 + h * 1024 + 512), "r"(ob[4][h]), "r"(ob[5][h]), "r"(ob[6][h]), "r"(ob[7][h]) : "memory");
            asm volatile("st.shared.v2.u32 [%0], {%1,%2};" ::"r"(sl + o1 + h * 256), "r"(ob[8][h]), "r"(ob[9][h]) : "memory");
        }
        if (wg && lane == 0) mbar_arrive(bars + 384 + 8 * warp);
        fence_async_smem();
        __syncwarp();
        TSTAMP1T(4, 64); CSA(6);
        TSTAMP1(1);
        TSTAMP2(1);
        const unsigned char* ot = reinterpret_cast<const unsigned char*>(of) + mb * 163840 + wg * 10240;
        if (lane == 0) {
            asm volatile("cp.async.bulk.global.shared::cta.bulk_group [%0], [%1], 2048;" ::"l"(ot + hg * 20480 + (warp & 3) * 2048), "r"(sl + (warp & 3) * 2048) : "memory");
            asm volatile("cp.async.bulk.global.shared::cta.bulk_group [%0], [%1], 512;" ::"l"(ot + hg * 20480 + 8192 + (warp & 3) * 512), "r"(sl + 8192 + (warp & 3) * 512) : "memory");
            asm volatile("cp.async.bulk.commit_group;" ::: "memory");
            if (wg == 0) mbar_arrive(bar_pv);
            asm volatile("cp.async.bulk.wait_group 0;" ::: "memory");
            asm volatile(A1_FRED " [%0], 1;" ::"l"(reinterpret_cast<uint32_t*>(rsum + 2 * SEQ) + (((layer * 16 + mb) * 2 + wg) * 8 + hg) * FSTR) : "memory");
            DBGC(4 + warp);
        }
        TSTAMP4(11); CSA(7);
        float ac2[40];
        const uint64_t db0 = make_desc(sbase, 1024, 256, 3), db1 = make_desc(sbase + 10240, 512, 256, 3), da0 = make_desc(sl, 16, 1024, 2), da1 = make_desc(sl + 8192, 16, 256, 3);
        const uint32_t o7 = wg ? 640 : (A1_SM_W0 - A1_SM_A0) >> 4;
        const uint32_t trow = ((lane & 7) + 8 * (lane >> 4)) * 128 + (((2 * (warp & 3) + ((lane >> 3) & 1)) ^ (lane & 7)) << 4);
        uint32_t xr[10][2];
        mbar_wait(bar_f2 + 64 * wg + 64, 0);
        if (layer == 0) {
#pragma unroll
            for (int j = 0; j < 10; j += 2) ldsm_x4(&xr[j][0], sl + 51200 + (16 * (warp & 3) + (lane & 15)) * 160 + (lane >> 4) * 16 + 16 * j);
        } else {
#pragma unroll
            for (int j = 0; j < 10; j += 2) ldsm_x4_t(&xr[j][0], sl + 51200 + trow + 1024 * j);
        }
        const uint32_t ri = __shfl_sync(~0u, layer * SEQ + (wg * 2 + ((g >> 1) & 1)) * 512 + (mb * 16 + 4 * (warp & 3) + (g >> 2)) * 2 + (g & 1), lane);
        mbar_wait(bar_wo, 0);
        if (wg) mbar_wait(bar_pv, 0);
        if (wg) asm volatile("bar.sync 2, 128;" ::: "memory"); else asm volatile("bar.sync 1, 128;" ::: "memory");
        TSTAMP2(2); CSA(8);
#pragma unroll
        for (int q = 0; q < 8; q++) {
            uint32_t bo = wo_off(0) >> 4;
            if (q) {
                mbar_wait(bar_f2 + 64 * wg + 8 * q, 0);
                asm volatile("ld.shared.u32 %0, [%1];" : "=r"(bo) : "r"(que + 32 * wg + 4 * q) : "memory");
                bo = __shfl_sync(~0u, bo, 0);
                TSTAMP4(q);
                if (q % 3 == 1) CSA(9 + q / 3);
                if (q == 1 && (tid & 127) == 0) DBGC(29 + 8 * wg);
            }
            wgmma_fence();
#pragma unroll
            for (int j = 0; j < 5; j++) wgmma_n80(ac2, (j < 4 ? da0 : da1) + (q == 7 ? o7 : 0u) + (uint64_t)((q < 6 ? q * 640 : 0) + (j & 2) * 16 + (j & 1) * 2), (j < 4 ? db0 : db1) + bo + (uint64_t)((j & 2) * 160 + (j & 1) * 32), j || q);
            wgmma_commit();
            if (q == 0) {
                wgmma_wait<0>();
                if ((tid & 127) == 0) { mbar_arrive(bar_e2 + 16 * wg); mbar_arrive(bar_e2 + 8); }
            }
            if (q == 2 && wg) {
                wgmma_wait<1>();
                if (tid == 128) mbar_arrive(bar_e2 + 24);
            }
        }
        if ((tid & 127) == 0) DBGC(28 + wg * 8 + 7);
        TSTAMP2(3);
        wgmma_wait<0>();
        TSTAMP2(4); CSA(12);
        if (__any_sync(~0u, ac2[0] != ac2[0] || ac2[2] != ac2[2])) {
#pragma unroll
            for (int i = 0; i < 40; i++) ac2[i] = 0.f;
            uint32_t a[20], an[20];
            auto lda = [&](uint32_t (&r)[20], int h) {
#pragma unroll
                for (int u = 0; u < 4; u++)
                    asm volatile("ld.relaxed.gpu.global.v4.u32 {%0,%1,%2,%3}, [%4];" : "=r"(r[4 * u]), "=r"(r[4 * u + 1]), "=r"(r[4 * u + 2]), "=r"(r[4 * u + 3]) : "l"(ot + h * 20480 + o0 + u * 512) : "memory");
#pragma unroll
                for (int u = 0; u < 2; u++)
                    asm volatile("ld.relaxed.gpu.global.v2.u32 {%0,%1}, [%2];" : "=r"(r[16 + 2 * u]), "=r"(r[17 + 2 * u]) : "l"(ot + h * 20480 + o1 + u * 256) : "memory");
            };
            lda(an, 0);
#pragma unroll 5
            for (int k = lane; k < WOB / 16; k += 32)
                reinterpret_cast<uint4*>(stg + (sl - sbase))[k] = __ldcg(reinterpret_cast<const uint4*>(wo + hg * 8 * WOB) + k);
            __syncwarp();
#pragma unroll 1
            for (int h = 0; h < 8; h++) {
#pragma unroll 1
                for (int it = 0; it < SPIN_MAX; it++) {
                    uint32_t m = 0;
#pragma unroll
                    for (int k = 0; k < 20; k += 2) m = __vimax3_u32(m, an[k], an[k + 1]);
                    if (!__any_sync(~0u, m == ~0u)) break;
                    lda(an, h);
                }
#pragma unroll
                for (int k = 0; k < 20; k++) a[k] = an[k];
                lda(an, min(h + 1, 7));
                const uint32_t bp = h == hg ? sl : sbase + wo_off(h + (h < hg));
                const int r0 = 8 * ((lane & 7) >> 1) + 2 * (lane >> 3) + (lane & 1), r2 = 4 * ((lane & 7) >> 1) + 2 * ((lane >> 3) & 1) + (lane & 1);
#pragma unroll
                for (int n = 0; n < 10; n++) {
                    uint32_t b[12];
                    ldsm_x4_t(b, bp + (n >> 1) * 1024 + r0 * 32 + (((n ^ (r0 >> 2)) & 1) << 4));
                    ldsm_x4_t(b + 4, bp + 5120 + (n >> 1) * 1024 + r0 * 32 + (((n ^ (r0 >> 2)) & 1) << 4));
                    ldsm_x4_t(b + 8, bp + 10240 + (n >> 1) * 512 + r2 * 32 + (((n ^ (r2 >> 2)) & 1) << 4));
                    mma_bf16(ac2 + 4 * n, a[0], a[8], a[1], a[9], b[0], b[1]); mma_bf16(ac2 + 4 * n, a[2], a[10], a[3], a[11], b[2], b[3]);
                    mma_bf16(ac2 + 4 * n, a[4], a[12], a[5], a[13], b[4], b[5]); mma_bf16(ac2 + 4 * n, a[6], a[14], a[7], a[15], b[6], b[7]);
                    mma_bf16(ac2 + 4 * n, a[16], a[18], a[17], a[19], b[8], b[9]);
                }
            }
        }
#pragma unroll
        for (int j = 0; j < 10; j++)
#pragma unroll
            for (int hh = 0; hh < 2; hh++) {
                const uint32_t a = pack2(ac2[4 * j + 2 * hh], ac2[4 * j + 2 * hh + 1]);
                const __nv_bfloat162 r = __hadd2_rn(*reinterpret_cast<const __nv_bfloat162*>(&xr[j][hh]), *reinterpret_cast<const __nv_bfloat162*>(&a));
                xr[j][hh] = *reinterpret_cast<const uint32_t*>(&r);
            }
        const uint32_t so = sl + 30720;
#pragma unroll
        for (int j = 0; j < 10; j += 2) stsm_x4_t(so + trow + 1024 * j, xr[j][0], xr[j][1], xr[j + 1][0], xr[j + 1][1]);
        if (wg) asm volatile("bar.sync 2, 128;" ::: "memory"); else asm volatile("bar.sync 1, 128;" ::: "memory");
        TSTAMP2(5); CSA(13);
        if ((tid & 127) == 0) {
            fence_async_smem();
            asm volatile("cp.async.bulk.tensor.2d.global.shared::cta.bulk_group [%0, {%1, %2}], [%3];" ::"l"(&tmX1), "r"(mb * 128 + 64 * wg), "r"(hg * 80), "r"(so) : "memory");
            asm volatile("cp.async.bulk.commit_group;" ::: "memory");
        }
        __syncwarp();
        const float p0 = *(volatile const float*)&rw[g].x, p1 = *(volatile const float*)&rw[g + 8].x;
        float s[3][4] = {};
        const uint32_t pp[2] = {__byte_perm(__float_as_uint(p0), 0, 0x3232), __byte_perm(__float_as_uint(p1), 0, 0x3232)};
#pragma unroll
        for (int j = 0; j < 10; j += 2) {
            const uint32_t d0 = sub2(xr[j][0], pp[0]), d1 = sub2(xr[j][1], pp[1]), d2 = sub2(xr[j + 1][0], pp[0]), d3 = sub2(xr[j + 1][1], pp[1]);
            mma_bf16(s[0], xr[j][0], xr[j][1], xr[j + 1][0], xr[j + 1][1], 0x3f803f80u, 0x3f803f80u);
            mma_bf16(s[1], d0, d1, d2, d3, d0, d2);
            mma_bf16(s[2], d0, d1, d2, d3, d1, d3);
        }
        if (t == (g >> 1)) {
            float2* rp = rsum + ri;
            asm volatile("red.relaxed.gpu.global.add.v2.f32 [%0], {%1, %2};" ::"l"(rp), "f"(fmaf(-80.f, p0, s[0][0])), "f"((g & 1) ? s[1][1] : s[1][0]) : "memory");
            asm volatile("red.relaxed.gpu.global.add.v2.f32 [%0], {%1, %2};" ::"l"(rp + 4), "f"(fmaf(-80.f, p1, s[0][2])), "f"((g & 1) ? s[2][3] : s[2][2]) : "memory");
        }
        asm volatile("cp.async.bulk.wait_group.read 0;" ::: "memory");
        TSTAMP2(6); CSA(14); CSA_END;
        if (tid == 0) DBGC(63);
        if (tid == 128) DBGC(28);
        if (tid == 0) DBGCAL(2);
        GSTAMP(g_tim1, 14);
        SPAN(1 + 4 * layer, 3);
    }
}

static int h_nsm;
static void* h_sym[11];
static TileTab h_tab[2];
static CUtensorMap h_tmX0, h_tmX1, h_tmR0, h_tmR1, h_tmX1st, h_tmOut, h_tmWq, h_tmWo, h_tmWt;
typedef CUresult (*PFN_encodeTiled)(CUtensorMap*, CUtensorMapDataType, cuuint32_t, void*, const cuuint64_t*, const cuuint64_t*,
                                    const cuuint32_t*, const cuuint32_t*, CUtensorMapInterleave, CUtensorMapSwizzle,
                                    CUtensorMapL2promotion, CUtensorMapFloatOOBfill);
static void make_tmap(CUtensorMap* tm, const void* ptr, uint64_t cols, uint64_t rows, uint32_t bc, uint32_t br, CUtensorMapSwizzle sw, uint64_t pitch = 0, uint64_t hi = 0, uint32_t bh = 2) {
    static PFN_encodeTiled fn = nullptr;
    if (!fn) {
        void* p = nullptr; cudaDriverEntryPointQueryResult qr;
        cudaGetDriverEntryPoint("cuTensorMapEncodeTiled", &p, cudaEnableDefault, &qr);
        fn = (PFN_encodeTiled)p;
    }
    if (br == 0) {
        cuuint64_t dims[5] = {16, 2, rows / 8, 4, cols / 16}; cuuint64_t strides[4] = {cols * 2, cols * 16, cols * 4, 32};
        cuuint32_t box[5] = {16, 2, bc, 4, 5}; cuuint32_t es[5] = {1, 1, 1, 1, 1};
        fn(tm, CU_TENSOR_MAP_DATA_TYPE_BFLOAT16, 5, const_cast<void*>(ptr), dims, strides, box, es, CU_TENSOR_MAP_INTERLEAVE_NONE, sw,
           CU_TENSOR_MAP_L2_PROMOTION_L2_128B, CU_TENSOR_MAP_FLOAT_OOB_FILL_NONE);
        return;
    }
    if (bh == 0) {
        cuuint64_t dims[5] = {64, 64, 2, 16, 10}; cuuint64_t strides[4] = {pitch * 2, hi * 2, cols * 2, rows * 2};
        cuuint32_t box[5] = {64, 64, 2, 1, 1}; cuuint32_t es[5] = {1, 1, 1, 1, 1};
        fn(tm, CU_TENSOR_MAP_DATA_TYPE_BFLOAT16, 5, const_cast<void*>(ptr), dims, strides, box, es, CU_TENSOR_MAP_INTERLEAVE_NONE, sw,
           CU_TENSOR_MAP_L2_PROMOTION_L2_128B, CU_TENSOR_MAP_FLOAT_OOB_FILL_NONE);
        return;
    }
    if (hi) {
        cuuint64_t dims[3] = {cols, rows, hi == 64 ? 32u : hi == 16 ? 120u : 2u}; cuuint64_t strides[2] = {pitch * 2, hi * 2};
        cuuint32_t box[3] = {bc, br, bh}; cuuint32_t es[3] = {1, 1, 1};
        fn(tm, CU_TENSOR_MAP_DATA_TYPE_BFLOAT16, 3, const_cast<void*>(ptr), dims, strides, box, es, CU_TENSOR_MAP_INTERLEAVE_NONE, sw,
           CU_TENSOR_MAP_L2_PROMOTION_L2_128B, CU_TENSOR_MAP_FLOAT_OOB_FILL_NONE);
        return;
    }
    cuuint64_t dims[2] = {cols, rows}; cuuint64_t strides[1] = {(pitch ? pitch : cols) * 2};
    cuuint32_t box[2] = {bc, br}; cuuint32_t es[2] = {1, 1};
    fn(tm, CU_TENSOR_MAP_DATA_TYPE_BFLOAT16, 2, const_cast<void*>(ptr), dims, strides, box, es, CU_TENSOR_MAP_INTERLEAVE_NONE, sw,
       CU_TENSOR_MAP_L2_PROMOTION_L2_128B, CU_TENSOR_MAP_FLOAT_OOB_FILL_NONE);
}
template <typename... Args>
static void launch_pdl(void (*kern)(Args...), int grid, int block, int smem, Args... args) {
    cudaLaunchConfig_t cfg = {};
    cfg.gridDim = dim3(grid); cfg.blockDim = dim3(block); cfg.dynamicSmemBytes = smem; cfg.stream = cudaStreamPerThread;
    cudaLaunchAttribute at[1];
    at[0].id = cudaLaunchAttributeProgrammaticStreamSerialization; at[0].val.programmaticStreamSerializationAllowed = 1;
    cfg.attrs = at; cfg.numAttrs = 1;
    cudaLaunchKernelEx(&cfg, kern, args...);
}
static void launch_stage(int k, void* const* d_in, void* d_out) {
    const KgIn kg = {(const bf16*)d_in[4], (const bf16*)d_in[5], (const bf16*)d_in[6], (const bf16*)d_in[7], (const bf16*)d_in[8], (const bf16*)d_in[9], (const bf16*)d_in[0], (const bf16*)d_in[1], (const bf16*)d_in[2],
                      (uint4*)h_sym[0], (uint4*)h_sym[1], (uint4*)h_sym[2], (uint4*)h_sym[3], (uint4*)h_sym[4], (float*)h_sym[5]};
    switch (k) {
        case 0: kgen_kernel<<<128, 512, KG_SMEM, cudaStreamPerThread>>>(kg, h_tmWq, h_tmWo, h_tmWt); break;
        case 1: launch_pdl(h_nsm == 132 ? a1_kernel<true> : a1_kernel<false>, h_nsm, A1_THREADS, A1_SMEM, 0, (const bf16*)d_in[0], (const unsigned char*)h_sym[2], (float2*)h_sym[4], (uint4*)h_sym[6], h_tmX0, h_tmR0, h_tmX1st, h_tab[0]); break;
        case 3: launch_pdl(conv_kernel, DM / CV_CPB, CV_THREADS, CV_SMEM, 0, (const uint4*)h_sym[7], (const float4*)h_sym[4], (const bf16*)h_sym[8], (bf16*)h_sym[9], (const uint4*)h_sym[0], h_tmOut); break;
        case 5: launch_pdl(h_nsm == 132 ? a1_kernel<true> : a1_kernel<false>, h_nsm, A1_THREADS, A1_SMEM, 1, (const bf16*)d_in[0], (const unsigned char*)h_sym[2], (float2*)h_sym[4], (uint4*)h_sym[6], h_tmX1, h_tmR1, h_tmX1st, h_tab[1]); break;
        case 7: launch_pdl(conv_kernel, DM / CV_CPB, CV_THREADS, CV_SMEM, 1, (const uint4*)h_sym[7] + SEQ / 8, (const float4*)h_sym[4] + SEQ / 2, (const bf16*)h_sym[8], (bf16*)h_sym[10], (const uint4*)h_sym[0], h_tmOut); break;
        default: break;
    }
}
static int n_stage_kernels() { return 9; }
static const char* stage_name(int k) { const char* n[] = {"kgen", "a1", "a2", "conv", "tr", "a1", "a2", "conv", "tr"}; return n[k]; }

extern "C" void kernel_launch(void* const* d_in, const int* in_sizes, int n_in, void* d_out, int out_size) {
    (void)in_sizes; (void)n_in; (void)out_size;
    static const void *p_in = nullptr, *p_w1 = nullptr, *p_w2 = nullptr, *p_out = nullptr;
    if (p_in != d_in[0] || p_w1 != d_in[1] || p_w2 != d_in[2] || p_out != d_out) {
        cudaFuncSetAttribute(conv_kernel, cudaFuncAttributeMaxDynamicSharedMemorySize, CV_SMEM);
        cudaFuncSetAttribute(kgen_kernel, cudaFuncAttributeMaxDynamicSharedMemorySize, KG_SMEM);
        cudaFuncSetAttribute(a1_kernel<true>, cudaFuncAttributeMaxDynamicSharedMemorySize, A1_SMEM);
        cudaFuncSetAttribute(a1_kernel<false>, cudaFuncAttributeMaxDynamicSharedMemorySize, A1_SMEM);
        int dev; cudaGetDevice(&dev); cudaDeviceGetAttribute(&h_nsm, cudaDevAttrMultiProcessorCount, dev);
        if (h_nsm != 132) h_nsm = 128;
        cudaGetSymbolAddress(&h_sym[0], g_tap); cudaGetSymbolAddress(&h_sym[1], g_wq); cudaGetSymbolAddress(&h_sym[2], g_wo);
        cudaGetSymbolAddress(&h_sym[3], g_halo); cudaGetSymbolAddress(&h_sym[4], g_sum); cudaGetSymbolAddress(&h_sym[5], g_csp); cudaGetSymbolAddress(&h_sym[6], g_of);
        cudaGetSymbolAddress(&h_sym[7], g_piv); cudaGetSymbolAddress(&h_sym[8], g_x1T); cudaGetSymbolAddress(&h_sym[9], g_xcT); cudaGetSymbolAddress(&h_sym[10], g_yT);
        for (int i = 0; i < 264; i++) {
            const int s = i % 132, h = (s - 64) >> 1;
            const int t = h_nsm != 132 ? s : s < 64 ? ((s >> 1) & 7) * 16 + (s >> 4) * 2 + (s & 1) : s < 120 ? (1 + h % 7) * 16 + 8 + (h / 7) * 2 + (s & 1) : s < 124 ? 128 : s - 116;
            const int hg = (4 * (t >> 6) + (t & 3)) & 7;
            const uint64_t wp = (uint64_t)h_sym[1] + hg * 10 * WQ_STAGE;
            h_tab[i / 132].e[s] = make_uint4((uint32_t)wp, (uint32_t)(wp >> 32), ((t >> 2) & 15) | (i / 132) << 4 | hg << 8 | 5 * (hg >> 2) << 16 | (uint32_t)t << 24, 0);
        }
        for (int i = 0; i < 56; i++) {
            const uint32_t c = i < 4 || i == 30 ? 0 : i < 8 || (i > 20 && i < 26) || i == 49 ? 2 : i == 8 || i == 27 ? 3 : i == 28 ? 4 : i == 29 ? 8 : 1;
            for (int l = 0; l < 2; l++) h_tab[l].cnt[i / 7] = (i % 7 ? h_tab[l].cnt[i / 7] : 0) | c << (4 * (i % 7));
        }
        void *px1, *px2;
        cudaGetSymbolAddress(&px1, g_x1T); cudaGetSymbolAddress(&px2, g_xcT);
        make_tmap(&h_tmX0, d_in[0], 128 * 640, 64, 64, 64, CU_TENSOR_MAP_SWIZZLE_128B, 1280, 640, 0);
        make_tmap(&h_tmX1, px2, 128, 64 * XCP, 64, 64, CU_TENSOR_MAP_SWIZZLE_128B, XCP, 64, 0);
        make_tmap(&h_tmR0, d_in[0], 640, 1024, 80, 64, CU_TENSOR_MAP_SWIZZLE_NONE, 1280, 640, 1);
        make_tmap(&h_tmR1, px2, 64, 640, 64, 80, CU_TENSOR_MAP_SWIZZLE_128B, XCP, 64, 1);
        make_tmap(&h_tmX1st, px1, 2048, 640, 64, 80, CU_TENSOR_MAP_SWIZZLE_128B, XCP);
        make_tmap(&h_tmWq, d_in[1], 16, 640, 16, 32, CU_TENSOR_MAP_SWIZZLE_32B, 1920, 16, 5);
        make_tmap(&h_tmWo, d_in[2], 640, 640, 4, 0, CU_TENSOR_MAP_SWIZZLE_32B);
        make_tmap(&h_tmWt, d_in[2], 640, 640, 2, 0, CU_TENSOR_MAP_SWIZZLE_32B);
        make_tmap(&h_tmOut, d_out, 640, 1024, 80, 8, CU_TENSOR_MAP_SWIZZLE_NONE, 1280, 640, 1);
        p_in = d_in[0]; p_w1 = d_in[1]; p_w2 = d_in[2]; p_out = d_out;
    }
    for (int k = 0; k < n_stage_kernels(); k++) launch_stage(k, d_in, d_out);
}
```

```cpp
#include <cuda_runtime.h>
#include <cuda_bf16.h>
#include <stdint.h>
#include <cuda.h>

typedef __nv_bfloat16 bf16;

constexpr int SEQ = 2048;
constexpr int DM = 640;
constexpr int NMODE = 192;

__device__ __forceinline__ float bf2f(bf16 v) { return __bfloat162float(v); }
__device__ __forceinline__ float rbf(float v) {
    uint32_t r;
    asm("cvt.rn.bf16x2.f32 %0, %1, %2;" : "=r"(r) : "f"(v), "f"(0.f));
    return __uint_as_float(r);
}
__device__ __forceinline__ uint32_t pack2(float lo, float hi) {
    __nv_bfloat162 t = __floats2bfloat162_rn(lo, hi);
    return *reinterpret_cast<uint32_t*>(&t);
}
__device__ __forceinline__ void pdl_sync() {
    asm volatile("griddepcontrol.wait;" ::: "memory");
    asm volatile("griddepcontrol.launch_dependents;" ::: "memory");
}
__device__ __forceinline__ float sqrt_apx(float v) { float r; asm("sqrt.approx.ftz.f32 %0, %1;" : "=f"(r) : "f"(v)); return r; }
__device__ __forceinline__ float rcp_apx(float v) { float r; asm("rcp.approx.ftz.f32 %0, %1;" : "=f"(r) : "f"(v)); return r; }
__device__ __forceinline__ uint32_t smem_u32(const void* p) { return (uint32_t)__cvta_generic_to_shared(p); }

constexpr int TAPB = 2944, TAPE = 928;
__device__ __align__(128) uint4 g_tap[DM * TAPB / 16];
#define XPAD 64
constexpr int XCP = SEQ + XPAD;
__device__ __align__(128) bf16 g_x1T[DM * XCP];
__device__ __align__(128) bf16 g_xcT[DM * XCP];
__device__ __align__(128) uint4 g_of[128 * 1280];
constexpr int WQ_STAGE = 240 * 128, WOB = 80 * 160;
__device__ __align__(128) uint4 g_wq[8 * 10 * WQ_STAGE / 16];
__device__ __align__(128) uint4 g_wo[64 * WOB / 16];
__device__ __align__(16) float g_csp[10 * 1920];
#define FSTR 32
__device__ __align__(128) float2 g_sum[2 * SEQ + 256 * FSTR];
__device__ __align__(16) bf16 g_piv[2 * SEQ];
__device__ __align__(128) bf16 g_yT[DM * XCP];
__device__ uint32_t g_epoch;
__device__ __align__(16) unsigned long long g_rstat[SEQ];
__device__ __align__(128) uint4 g_halo[640 * 148];
__device__ __forceinline__ unsigned long long tagw(uint32_t payload, uint32_t tag) { return ((unsigned long long)tag << 32) | payload; }
__device__ __forceinline__ ulonglong2 ld_tag2(const ulonglong2* p) {
    ulonglong2 v;
    asm volatile("ld.relaxed.gpu.global.v2.u64 {%0, %1}, [%2];" : "=l"(v.x), "=l"(v.y) : "l"(p) : "memory");
    return v;
}
__device__ __forceinline__ bool tag_ok(ulonglong2 v, uint32_t tag) { return (uint32_t)(v.x >> 32) == tag && (uint32_t)(v.y >> 32) == tag; }
__device__ __forceinline__ uint32_t ld_epoch() { uint32_t v; asm volatile("ld.relaxed.gpu.global.u32 %0, [%1];" : "=r"(v) : "l"(&g_epoch) : "memory"); return v + 1; }
constexpr int SPIN_MAX = 1 << 20;
__device__ uint32_t g_started[4];
__device__ __forceinline__ void sm_started(int slot) { asm volatile("red.relaxed.gpu.global.add.u32 [%0], 1;" ::"l"(g_started + slot) : "memory"); }
__device__ __noinline__ void sm_idle(int slot) {
    if (threadIdx.x) return;
    sm_started(slot);
    const uint32_t want = ld_epoch() * gridDim.x;
    pdl_sync();
#pragma unroll 1
    for (int it = 0; it < SPIN_MAX; it++) {
        uint32_t v;
        asm volatile("ld.relaxed.gpu.global.u32 %0, [%1];" : "=r"(v) : "l"(g_started + slot) : "memory");
        if ((int)(v - want) >= 0) break;
        __nanosleep(100);
    }
}
struct TileTab { uint4 e[132]; uint32_t cnt[8]; };
__device__ __forceinline__ bool elect() {
    uint32_t p;
    asm volatile("{\n.reg .pred p;\nelect.sync _|p, 0xffffffff;\nselp.b32 %0, 1, 0, p;\n}" : "=r"(p));
    return p;
}
#define DBG_SYMS
#define TSTAMP(i)
#define TSTAMP1(i)
#define TSTAMP1T(i, t)
#define TSTAMP1X(i, t)
#define SPAN(k, i)
#define GSTAMP(arr, i)
#define TSTAMP2(i)
#define TSTAMP3(i)
#define TSTAMP4(i)
#define TSTAMPK(i, t)
#define TSTAMPC(i)
#define DBGC(i)
#define DBGV(i, v)
#define DBGCAL(i)

#define CSK(i)
#define CSK_END
#define CSA(i)
#define CSA_END
#define CST(i)
#define CST_END
#define CST_EXTRA 0
__device__ __forceinline__ void mma_bf16(float* d, uint32_t a0, uint32_t a1, uint32_t a2, uint32_t a3, uint32_t b0, uint32_t b1) {
    asm volatile("mma.sync.aligned.m16n8k16.row.col.f32.bf16.bf16.f32 {%0,%1,%2,%3}, {%4,%5,%6,%7}, {%8,%9}, {%0,%1,%2,%3};"
                 : "+f"(d[0]), "+f"(d[1]), "+f"(d[2]), "+f"(d[3]) : "r"(a0), "r"(a1), "r"(a2), "r"(a3), "r"(b0), "r"(b1));
}
__device__ __forceinline__ void mma_bf16_k8(float* d, uint32_t a0, uint32_t a1, uint32_t b0) {
    asm volatile("mma.sync.aligned.m16n8k8.row.col.f32.bf16.bf16.f32 {%0,%1,%2,%3}, {%4,%5}, {%6}, {%0,%1,%2,%3};"
                 : "+f"(d[0]), "+f"(d[1]), "+f"(d[2]), "+f"(d[3]) : "r"(a0), "r"(a1), "r"(b0));
}
__device__ __forceinline__ void ldsm_x4(uint32_t* r, uint32_t addr) {
    asm volatile("ldmatrix.sync.aligned.m8n8.x4.shared.b16 {%0,%1,%2,%3}, [%4];"
                 : "=r"(r[0]), "=r"(r[1]), "=r"(r[2]), "=r"(r[3]) : "r"(addr));
}

__device__ __forceinline__ void ldsm_x4_t(uint32_t* r, uint32_t addr) {
    asm volatile("ldmatrix.sync.aligned.m8n8.x4.trans.shared.b16 {%0,%1,%2,%3}, [%4];"
                 : "=r"(r[0]), "=r"(r[1]), "=r"(r[2]), "=r"(r[3]) : "r"(addr));
}
__device__ __forceinline__ void mbar_init(uint32_t bar, int count) { asm volatile("mbarrier.init.shared::cta.b64 [%0], %1;" ::"r"(bar), "r"(count)); }
__device__ __forceinline__ void mbar_arrive(uint32_t bar) { asm volatile("mbarrier.arrive.shared::cta.b64 _, [%0];" ::"r"(bar) : "memory"); }
__device__ __forceinline__ void mbar_wait(uint32_t bar, uint32_t parity) {
    asm volatile("{\n.reg .pred p;\nWAIT_LOOP:\n"
                 "mbarrier.try_wait.parity.shared::cta.b64 p, [%0], %1;\n"
                 "@p bra.uni WAIT_DONE;\nbra.uni WAIT_LOOP;\nWAIT_DONE:\n}" ::"r"(bar), "r"(parity) : "memory");
}

__device__ __forceinline__ void mbar_expect_tx(uint32_t bar, uint32_t bytes) {
    asm volatile("mbarrier.arrive.expect_tx.shared::cta.b64 _, [%0], %1;" ::"r"(bar), "r"(bytes) : "memory");
}
__device__ __forceinline__ void tma_load_2d(uint32_t dst, const void* tmap, int c0, int c1, uint32_t bar) {
    asm volatile("cp.async.bulk.tensor.2d.shared::cluster.global.mbarrier::complete_tx::bytes [%0], [%1, {%3, %4}], [%2];"
                 ::"r"(dst), "l"(tmap), "r"(bar), "r"(c0), "r"(c1) : "memory");
}
__device__ __forceinline__ void tma_load_3d(uint32_t dst, const void* tmap, int c0, int c1, int c2, uint32_t bar) {
    asm volatile("cp.async.bulk.tensor.3d.shared::cluster.global.mbarrier::complete_tx::bytes [%0], [%1, {%3, %4, %5}], [%2];"
                 ::"r"(dst), "l"(tmap), "r"(bar), "r"(c0), "r"(c1), "r"(c2) : "memory");
}
__device__ __forceinline__ void fence_async_smem() { asm volatile("fence.proxy.async.shared::cta;" ::: "memory"); }
__device__ __forceinline__ void bulk_load(uint32_t dst, const void* src, uint32_t bytes, uint32_t bar) {
    asm volatile("cp.async.bulk.shared::cluster.global.mbarrier::complete_tx::bytes [%0], [%1], %2, [%3];"
                 ::"r"(dst), "l"(src), "r"(bytes), "r"(bar) : "memory");
}
__device__ __forceinline__ void stsm_x4(uint32_t addr, uint32_t r0, uint32_t r1, uint32_t r2, uint32_t r3) {
    asm volatile("stmatrix.sync.aligned.m8n8.x4.shared.b16 [%0], {%1,%2,%3,%4};" ::"r"(addr), "r"(r0), "r"(r1), "r"(r2), "r"(r3) : "memory");
}
__device__ __forceinline__ void stsm_x4_t(uint32_t addr, uint32_t r0, uint32_t r1, uint32_t r2, uint32_t r3) {
    asm volatile("stmatrix.sync.aligned.m8n8.x4.trans.shared.b16 [%0], {%1,%2,%3,%4};" ::"r"(addr), "r"(r0), "r"(r1), "r"(r2), "r"(r3) : "memory");
}
__device__ __forceinline__ void prefetch_tmap(const void* tmap) { asm volatile("prefetch.tensormap [%0];" ::"l"(tmap) : "memory"); }

__device__ __forceinline__ float2 cexp_at(float wr2, float wi, float p) {
    float er;
    asm("ex2.approx.ftz.f32 %0, %1;" : "=f"(er) : "f"(wr2 * p));
    float th = wi * p;
    const float k = rintf(th * 0.15915494309189535f);
    th = fmaf(k, -6.2831854820251465f, th);
    th = fmaf(k, 1.7484555314695172e-7f, th);
    return make_float2(er * __cosf(th), er * __sinf(th));
}
__device__ __forceinline__ float2 cmul(float2 a, float2 b) {
    return make_float2(fmaf(a.x, b.x, -a.y * b.y), fmaf(a.x, b.y, a.y * b.x));
}
__device__ __forceinline__ float2 csqr(float2 a) { return make_float2(fmaf(a.x, a.x, -a.y * a.y), (a.x + a.x) * a.y); }
__device__ __forceinline__ uint32_t packh(float2 v) {
    uint32_t r;
    asm("cvt.rn.f16x2.f32 %0, %1, %2;" : "=r"(r) : "f"(v.y), "f"(v.x));
    return r;
}
__device__ __forceinline__ void mma_f16(float* d, uint32_t a0, uint32_t a1, uint32_t a2, uint32_t a3, uint32_t b0, uint32_t b1) {
    asm volatile("mma.sync.aligned.m16n8k16.row.col.f32.f16.f16.f32 {%0,%1,%2,%3}, {%4,%5,%6,%7}, {%8,%9}, {%0,%1,%2,%3};"
                 : "+f"(d[0]), "+f"(d[1]), "+f"(d[2]), "+f"(d[3]) : "r"(a0), "r"(a1), "r"(a2), "r"(a3), "r"(b0), "r"(b1));
}

struct KgIn { const bf16 *logA, *Aim, *Cre, *Cim, *logdt, *dsk, *x, *wqkv, *wo; uint4 *tap, *wq, *wop, *halo, *sum; float* csp; };
constexpr int KG_THREADS = NMODE / 2;

constexpr int KG_BUF = 15 * 12288, KG_BAR = KG_BUF + 6 * 5120, KG_SMEM = KG_BAR + 64 + CST_EXTRA;
__global__ void __launch_bounds__(512, 1) kgen_kernel(const KgIn in, const __grid_constant__ CUtensorMap tmWq, const __grid_constant__ CUtensorMap tmWo,
                                                        const __grid_constant__ CUtensorMap tmWt) {
    extern __shared__ __align__(1024) uint4 tabs[];
#define KG_ROT 0
    CSK(0);
    const int lane = threadIdx.x & 31;
    SPAN(0, 0); SPAN(0, 1);
    TSTAMPK(0, 0);
    if (threadIdx.x >= 480) {
        asm volatile("griddepcontrol.launch_dependents;" ::: "memory");
        const uint32_t b0 = smem_u32(tabs) + KG_BUF, wbar = b0 + 6 * 5120;
        const int blk = blockIdx.x, nq = blk < 112 ? 4 : 2, nj = nq + (blk < 64 ? 1 : 2);
        auto fetch = [&](int i) {
            const uint32_t dst = b0 + i * 5120, bar = wbar + 8 * i;
            if (i < nq) {
                const int p = blk + 64 * (i & 2), kb = p / 24;
                mbar_expect_tx(bar, 5120);
                tma_load_3d(dst, &tmWq, 0, kb * 64 + (i & 1) * 32, (p - 24 * kb) * 5, bar);
            } else {
                const int o = i == nq ? blk : 255 - blk;
                mbar_expect_tx(bar, o < 128 ? 5120 : 2560);
                asm volatile("cp.async.bulk.tensor.5d.shared::cluster.global.mbarrier::complete_tx::bytes [%0], [%1, {%3, %3, %4, %3, %5}], [%2];"
                             ::"r"(dst), "l"(o < 128 ? &tmWo : &tmWt), "r"(bar), "r"(0), "r"((o & 7) * 10 + (o >> 6) * 4), "r"(((o >> 3) & 7) * 5) : "memory");
            }
        };
        const bool one = elect();
        if (one) {
#pragma unroll
            for (int i = 0; i < 6; i++) mbar_init(wbar + 8 * i, 1);
            asm volatile("fence.mbarrier_init.release.cluster;" ::: "memory");
#pragma unroll 1
            for (int i = 0; i < nj; i++) fetch(i);
            CSK(1);
#pragma unroll 1
            for (int i = 0; i < nj; i++) {
                const int p = blk + 64 * (i & 2), kb = p / 24, hg = p & 7, sec = (p - 24 * kb) >> 3, o = i == nq ? blk : 255 - blk, cg = (o >> 3) & 7, hb = o & 7;
                const unsigned char* dst = i < nq ? reinterpret_cast<unsigned char*>(in.wq) + (hg * 10 + (hg < 4 ? kb : kb < 5 ? kb + 5 : kb - 5)) * WQ_STAGE + ((i & 1) * 3 + sec) * 5120
                                                  : reinterpret_cast<unsigned char*>(in.wop) + (cg * 8 + (hb == cg ? 0 : hb + (hb < cg))) * WOB + (o >> 6) * 5120;
                mbar_wait(wbar + 8 * i, 0);
                CSK(2 + i);
                if (i == 0) TSTAMPK(2, (15 - KG_ROT) * 32);
                if (i == 3) TSTAMPK(5, (15 - KG_ROT) * 32);
                asm volatile("cp.async.bulk.global.shared::cta.bulk_group [%0], [%1], %2;" ::"l"(dst), "r"(b0 + i * 5120), "r"(i < nq || o < 128 ? 5120 : 2560) : "memory");
            }
            asm volatile("cp.async.bulk.commit_group;" ::: "memory");
        }
        __syncwarp();
        CSK(8);
#pragma unroll 1
        for (int h = 0; 2 * h < nq; h++) {
            float cs[5][4] = {};
#pragma unroll
            for (int a = 0; a < 4; a++)
#pragma unroll
                for (int j = 0; j < 5; j++) {
                    uint32_t w[4];
                    ldsm_x4_t(w, b0 + h * 10240 + j * 1024 + ((lane >> 4) * 8 + (lane & 7)) * 32 + ((((lane >> 3) ^ (lane >> 2)) & 1) << 4) + (a >> 1) * 5120 + (a & 1) * 512);
                    mma_bf16(cs[j], w[0], w[1], w[2], w[3], 0x3f803f80u, 0x3f803f80u);
                }
#pragma unroll
            for (int j = 0; j < 5; j++)
                if ((lane & 3) < 2) in.csp[(blk + 128 * h) * 80 + j * 16 + (lane >> 2) + 8 * (lane & 3)] = (lane & 3) ? cs[j][2] : cs[j][0];
        }
        asm volatile("cp.async.bulk.wait_group.read 0;" ::: "memory");
        TSTAMPK(11, (15 - KG_ROT) * 32); CSK(9); CSK_END;
        return;
    }
    const int w16 = (__shfl_sync(~0u, threadIdx.x >> 5, 0) + KG_ROT) & 15, grp = w16 / 3, warp = w16 - 3 * grp;
    const int d = blockIdx.x * 5 + grp, tid = warp * 32 + lane;
    uint4* tab = tabs + grp * (3 * 768);
    asm volatile("griddepcontrol.launch_dependents;" ::: "memory");
    const bf16 pdt = in.logdt[d], pdsk = in.dsk[d];
    const uint32_t pla = reinterpret_cast<const uint32_t*>(in.logA)[d * KG_THREADS + tid], pai = reinterpret_cast<const uint32_t*>(in.Aim)[d * KG_THREADS + tid];
    const uint32_t pcr = reinterpret_cast<const uint32_t*>(in.Cre)[d * KG_THREADS + tid], pci = reinterpret_cast<const uint32_t*>(in.Cim)[d * KG_THREADS + tid];
    const bf16* pfq = tid < 30 ? in.wqkv + (size_t)(d * 30 + tid) * 64 : tid < 40 ? in.wo + (size_t)(d * 10 + tid - 30) * 64 : in.x + (size_t)(d * 32 + tid - 40) * 64;
#define KG_PF 0
    if (tid < (KG_PF == 3 ? 0 : KG_PF ? 40 : 72)) asm volatile("prefetch.global.L2 [%0];" ::"l"(pfq));
    asm volatile("st.global.v4.u32 [%0], {%1,%1,%1,%1};" ::"l"(in.halo + d * 148 + tid), "r"(~0u));
    if (tid < 52) asm volatile("st.global.v4.u32 [%0], {%1,%1,%1,%1};" ::"l"(in.halo + d * 148 + 96 + tid), "r"(~0u));
    else if (w16 == 2) {
        if (lane < 16) in.sum[blockIdx.x * 16 + lane] = make_uint4(0, 0, 0, 0);
        else if (lane < 20) reinterpret_cast<uint32_t*>(in.sum + 2048)[(blockIdx.x * 4 + lane - 16) * FSTR] = 0;
    }
    CSK(1);
    const uint32_t tw = smem_u32(tab) + warp * 12288;
    const int g = lane >> 2, t = lane & 3;
    const uint32_t sta = tw + lane * 128 + ((2 * (lane & 3) + ((lane >> 2) & 1)) << 4);
    const uint32_t lda = tw + t * 128 + ((g ^ (2 * t)) << 4);
    const uint32_t stb = tw + lane * 8, ldb = tw + g * 512 + (g & 3) * 32 + t * 8;
    auto sts4 = [&](int e, int off, uint32_t a, uint32_t b, uint32_t c, uint32_t dd) {
        asm volatile("st.shared.v4.u32 [%0], {%1,%2,%3,%4};" ::"r"((sta ^ (e << 4)) + off), "r"(a), "r"(b), "r"(c), "r"(dd) : "memory");
    };
    auto lds4 = [&](int sp, int off, uint32_t* r) {
        asm volatile("ld.shared.v4.u32 {%0,%1,%2,%3}, [%4];" : "=r"(r[0]), "=r"(r[1]), "=r"(r[2]), "=r"(r[3]) : "r"((lda ^ ((sp & 1) << 4)) + sp * 512 + off) : "memory");
    };
    const float dt = rbf(expf(bf2f(pdt)));
    float2 C[2], y1[2], z8[2], y128[2];
    float cmax = 0.f;
#pragma unroll
    for (int m = 0; m < 2; m++) {
        const float wr2 = -rbf(expf(__uint_as_float(m ? pla & 0xffff0000u : pla << 16))) * dt * 1.4426950408889634f;
        const float wi = __uint_as_float(m ? pai & 0xffff0000u : pai << 16) * dt;
        C[m] = make_float2(__uint_as_float(m ? pcr & 0xffff0000u : pcr << 16) * dt, -__uint_as_float(m ? pci & 0xffff0000u : pci << 16) * dt);
        cmax = fmaxf(cmax, fmaxf(fabsf(C[m].x), fabsf(C[m].y)));
        y1[m] = cexp_at(wr2, -wi, 1.f); z8[m] = cexp_at(wr2, wi, 8.f); y128[m] = cexp_at(wr2, -wi, 128.f);
    }
    const int ex = min(max((int)(__reduce_max_sync(~0u, __float_as_uint(cmax)) >> 23), 20), 240);
    const float scale = __uint_as_float((uint32_t)(127 + 10 + 127 - ex) << 23), unscale = 2.0f * __uint_as_float((uint32_t)(ex - 10) << 23);
    TSTAMPK(4, 64); CSK(3);
    if (KG_PF >= 2 && tid >= 40 && tid < 72) asm volatile("prefetch.global.L2 [%0];" ::"l"(pfq));
    float k2048 = 0.f;
    float acc[5][4];
#pragma unroll
    for (int j = 0; j < 5; j++)
#pragma unroll
        for (int k = 0; k < 4; k++) acc[j][k] = 0.f;
    uint32_t af[8][4];
    {
        float2 h0[2], h1[2], g0[2], g1[2], g2[2], g2b[2], g3[2], g4[2], y2[2], y4[2];
#pragma unroll
        for (int m = 0; m < 2; m++) {
            h0[m] = make_float2(1.f, 0.f); h1[m] = csqr(csqr(csqr(z8[m])));
            g0[m] = make_float2(C[m].x * scale, C[m].y * scale);
            g1[m] = cmul(g0[m], y128[m]);
            const float2 y256 = csqr(y128[m]), y512 = csqr(y256);
            g2b[m] = g2[m] = cmul(g0[m], y256); g3[m] = cmul(g0[m], y512); g4[m] = cmul(g3[m], y512);
            y2[m] = csqr(y1[m]); y4[m] = csqr(y2[m]);
            const float2 y1024 = csqr(y512);
            k2048 += fmaf(g4[m].x, y1024.x, -g4[m].y * y1024.y);
        }
#pragma unroll
        for (int e = 0; e < 8; e++) {
            sts4(e, 0, packh(h0[0]), packh(h1[0]), packh(h0[1]), packh(h1[1]));
            sts4(e, 4096, packh(g0[0]), packh(g0[1]), packh(g1[0]), packh(g1[1]));
#pragma unroll
            for (int m = 0; m < 2; m++)
                if (e < 7) { h0[m] = e ? cmul(h0[m], z8[m]) : z8[m]; h1[m] = cmul(h1[m], z8[m]); g0[m] = cmul(g0[m], y1[m]); g1[m] = cmul(g1[m], y1[m]); }
            if (e < 5) k2048 += __shfl_xor_sync(~0u, k2048, 1 << e);
        }
        if (KG_PF == 1 && tid >= 40 && tid < 72) asm volatile("prefetch.global.L2 [%0];" ::"l"(pfq));
        __syncwarp();
        CSK(4);
#pragma unroll
        for (int e = 0; e < 8; e++) {
            uint32_t b[4];
            lds4(e, 0, af[e]); lds4(e, 4096, b);
            sts4(e, 8192, packh(g2[0]), packh(g2[1]), packh((e & 1) ? cmul(g3[0], y4[0]) : g3[0]), packh((e & 1) ? cmul(g3[1], y4[1]) : g3[1]));
            asm volatile("st.shared.v2.u32 [%0], {%1,%2};" ::"r"((stb ^ ((e & 3) << 5)) + e * 512), "r"(packh(g4[0])), "r"(packh(g4[1])) : "memory");
#pragma unroll
            for (int m = 0; m < 2; m++)
                if (e < 7) {
                    g2[m] = e == 3 ? cmul(g2b[m], y128[m]) : cmul(g2[m], y2[m]);
                    if (e & 1) g3[m] = cmul(g3[m], y128[m]);
                    g4[m] = cmul(g4[m], y128[m]);
                }
            mma_f16(acc[0], af[e][0], af[e][1], af[e][2], af[e][3], b[0], b[1]);
            mma_f16(acc[1], af[e][0], af[e][1], af[e][2], af[e][3], b[2], b[3]);
        }
    }
    TSTAMPK(6, 64); CSK(5);
    __syncwarp();
#pragma unroll
    for (int sp = 0; sp < 8; sp++) {
        uint32_t c[4], e0, e1;
        lds4(sp, 8192, c);
        asm volatile("ld.shared.v2.u32 {%0,%1}, [%2];" : "=r"(e0), "=r"(e1) : "r"(ldb ^ (sp << 5)) : "memory");
        mma_f16(acc[2], af[sp][0], af[sp][1], af[sp][2], af[sp][3], c[0], c[1]);
        mma_f16(acc[3], af[sp][0], af[sp][1], af[sp][2], af[sp][3], c[2], c[3]);
        mma_f16(acc[4], af[sp][0], af[sp][1], af[sp][2], af[sp][3], e0, e1);
    }
    {
        float* Pp = reinterpret_cast<float*>(tab + warp * 768);
        auto sw = [](int i) { return i ^ ((i >> 2) & 24); };
#pragma unroll
        for (int h = 0; h < 2; h++) {
            const int b = g + 8 * h;
            *reinterpret_cast<float2*>(Pp + sw(8 * b + 2 * t)) = make_float2(acc[0][2 * h] * unscale, acc[0][2 * h + 1] * unscale);
            *reinterpret_cast<float2*>(Pp + 128 + sw(8 * b + 2 * t)) = make_float2(acc[1][2 * h] * unscale, acc[1][2 * h + 1] * unscale);
            *reinterpret_cast<float2*>(Pp + 256 + sw(4 * b + 2 * (t & 1) + 64 * (t >> 1))) = make_float2(acc[2][2 * h] * unscale, acc[2][2 * h + 1] * unscale);
            *reinterpret_cast<float2*>(Pp + 384 + sw(2 * b + 32 * t)) = make_float2(acc[3][2 * h] * unscale, acc[3][2 * h + 1] * unscale);
            Pp[512 + sw(b + 32 * t)] = acc[4][2 * h] * unscale;
            Pp[512 + sw(b + 32 * t + 16)] = acc[4][2 * h + 1] * unscale;
        }
        if (lane == 0) Pp[640] = k2048 * unscale;
    }
    TSTAMPK(7, 64); CSK(6);
    asm volatile("bar.sync %0, 96;" ::"r"(grp + 1) : "memory");
    TSTAMPK(9, 64); CSK(7);
    const float* Kp = reinterpret_cast<const float*>(tab);
    auto ksum = [&](int i) -> float { return (Kp[i] + Kp[3072 + i]) + Kp[6144 + i]; };
    auto ksum4 = [&](int q) -> float4 {
        q ^= (q >> 2) & 6;
        const float4 a = reinterpret_cast<const float4*>(Kp)[q], b = reinterpret_cast<const float4*>(Kp)[768 + q], c = reinterpret_cast<const float4*>(Kp)[1536 + q];
        return make_float4((a.x + b.x) + c.x, (a.y + b.y) + c.y, (a.z + b.z) + c.z, (a.w + b.w) + c.w);
    };
    {
        uint2* W2 = reinterpret_cast<uint2*>(in.tap + d * (TAPB / 16)) + 8;
        uint2* E4 = W2 + (TAPE - 64) / 8;
        auto ksum2 = [&](int q) -> float2 {
            q ^= (q >> 2) & 12;
            const float2 a = reinterpret_cast<const float2*>(Kp)[q], b = reinterpret_cast<const float2*>(Kp)[1536 + q], c = reinterpret_cast<const float2*>(Kp)[3072 + q];
            return make_float2((a.x + b.x) + c.x, (a.y + b.y) + c.y);
        };
        float2 v = ksum2(64 * warp + lane), z = ksum2(64 * warp + 32 + lane);
        float4 u = ksum4(96 + min(tid, 64));
        const float cor = rbf(ksum(tid == 95 ? 384 : lane ? 512 : (128 * warp - 25) & 255));
        if (tid == 0) v.x += bf2f(pdsk);
        if (tid == 95) z.y -= cor;
        if (tid == 31) u.w -= cor;
        const uint32_t lo = pack2(v.x, v.y), hi = pack2(z.x, z.y);
        const int src = lane + (warp < 2 ? -1 : 1);
        uint32_t nl = __shfl_sync(~0u, tid == 64 ? hi : lo, src), nh = __shfl_sync(~0u, lane == 31 && warp < 2 ? lo : hi, src);
        if (tid < 64) {
            if (lane == 0) nl = warp ? __float_as_uint(cor) : 0u;
            W2[64 * warp + lane] = make_uint2(__byte_perm(lo, nl, 0x7610), __byte_perm(lo, 0, 0x1032));
            W2[64 * warp + lane + 32] = make_uint2(__byte_perm(hi, nh, 0x7610), __byte_perm(hi, 0, 0x1032));
            E4[(tid < 32 ? 159 : 209 - 32) + tid] = make_uint2(pack2(u.x, u.y), pack2(u.z, u.w));
        } else {
            reinterpret_cast<uint4*>(W2)[tid] = make_uint4(__byte_perm(lo, __float_as_uint(cor), lane ? 0x1010 : 0x7610), __byte_perm(lo, 0, 0x1010), __byte_perm(lo, 0, 0x1032), __byte_perm(nl, lo, 0x7610));
            reinterpret_cast<uint4*>(W2)[tid + 32] = make_uint4(__byte_perm(hi, 0, 0x1010), __byte_perm(hi, 0, 0x1010), __byte_perm(hi, 0, 0x1032), __byte_perm(tid == 95 ? 0u : nh, hi, 0x7610));
            if (tid == 64) E4[241] = make_uint2(pack2(u.x, 0.f), 0u);
        }
    }
    TSTAMPK(10, 64); CSK(8);
    CSK(9); CSK_END;
    SPAN(0, 3);
}

#define CV_SLEEP 40
#define CV_LD "ld.relaxed.gpu.global"
#define CV_NL 1
#define CV_D2 3
#define CV_PDH 12
#define CV_PDF 4
#define CV_HAND 7
constexpr int CV_CPB = 5;
constexpr int CV_THREADS = 512;
constexpr int UPADF = 128;
constexpr int ULEN = UPADF + SEQ;
constexpr int XLEN = XCP;
constexpr int BX_5 = 0, BX_3 = 3264, BX_9 = 6528, BX_7 = 8960, BX_LEN = 11392;
constexpr int CV_SM_U = 0;
constexpr int CV_SM_T = CV_CPB * ULEN * 2;
constexpr int CV_SM_B = CV_SM_T + CV_CPB * TAPB;
constexpr int CV_SM_X = CV_SM_B + CV_CPB * BX_LEN;
constexpr int CV_SM_Y = (CV_SM_X + CV_CPB * XLEN * 2 + 127) & ~127;
constexpr int CV_SM_CNT = CV_SM_Y + CV_CPB * 8192;
constexpr int CV_SM_O = CV_SM_CNT + 128;
constexpr int CV_SMEM = CV_SM_O + 20480 + CST_EXTRA;
static_assert(ULEN % 128 == 0 && CV_SM_B % 128 == 0 && CV_SM_CNT % 128 == 0, "layout");

__device__ __forceinline__ uint32_t sub2(uint32_t x, uint32_t m) {
    const __nv_bfloat162 d = __hsub2(*reinterpret_cast<const __nv_bfloat162*>(&x), *reinterpret_cast<const __nv_bfloat162*>(&m));
    return *reinterpret_cast<const uint32_t*>(&d);
}
__device__ __forceinline__ uint32_t add2(uint32_t x, uint32_t y) {
    const __nv_bfloat162 d = __hadd2_rn(*reinterpret_cast<const __nv_bfloat162*>(&x), *reinterpret_cast<const __nv_bfloat162*>(&y));
    return *reinterpret_cast<const uint32_t*>(&d);
}
__device__ __forceinline__ void wgmma_fence() { asm volatile("wgmma.fence.sync.aligned;" ::: "memory"); }
__device__ __forceinline__ void wgmma_commit() { asm volatile("wgmma.commit_group.sync.aligned;" ::: "memory"); }
template <int N> __device__ __forceinline__ void wgmma_wait() { asm volatile("wgmma.wait_group.sync.aligned %0;" ::"n"(N) : "memory"); }
__device__ __forceinline__ uint64_t make_desc(uint32_t addr, uint32_t lbo, uint32_t sbo, uint32_t mode) {
    return (uint64_t)((addr & 0x3FFFF) >> 4) | ((uint64_t)(lbo >> 4) << 16) | ((uint64_t)(sbo >> 4) << 32) | ((uint64_t)mode << 62);
}
__device__ __forceinline__ void wgmma_rs128(float (&d)[64], uint2 hi, uint2 lo, uint64_t db, int acc) {
    asm volatile("{\n.reg .pred p;\nsetp.ne.b32 p, %69, 0;\nwgmma.mma_async.sync.aligned.m64n128k16.f32.bf16.bf16 {%0,%1,%2,%3,%4,%5,%6,%7,%8,%9,%10,%11,%12,%13,%14,%15,%16,%17,%18,%19,%20,%21,%22,%23,%24,%25,%26,%27,%28,%29,%30,%31,%32,%33,%34,%35,%36,%37,%38,%39,%40,%41,%42,%43,%44,%45,%46,%47,%48,%49,%50,%51,%52,%53,%54,%55,%56,%57,%58,%59,%60,%61,%62,%63}, {%64,%65,%66,%67}, %68, p, 1, 1, 0;\n}"
                 : "+f"(d[0]), "+f"(d[1]), "+f"(d[2]), "+f"(d[3]), "+f"(d[4]), "+f"(d[5]), "+f"(d[6]), "+f"(d[7]), "+f"(d[8]), "+f"(d[9]), "+f"(d[10]), "+f"(d[11]), "+f"(d[12]), "+f"(d[13]), "+f"(d[14]), "+f"(d[15]), "+f"(d[16]), "+f"(d[17]), "+f"(d[18]), "+f"(d[19]), "+f"(d[20]), "+f"(d[21]), "+f"(d[22]), "+f"(d[23]), "+f"(d[24]), "+f"(d[25]), "+f"(d[26]), "+f"(d[27]), "+f"(d[28]), "+f"(d[29]), "+f"(d[30]), "+f"(d[31]), "+f"(d[32]), "+f"(d[33]), "+f"(d[34]), "+f"(d[35]), "+f"(d[36]), "+f"(d[37]), "+f"(d[38]), "+f"(d[39]), "+f"(d[40]), "+f"(d[41]), "+f"(d[42]), "+f"(d[43]), "+f"(d[44]), "+f"(d[45]), "+f"(d[46]), "+f"(d[47]), "+f"(d[48]), "+f"(d[49]), "+f"(d[50]), "+f"(d[51]), "+f"(d[52]), "+f"(d[53]), "+f"(d[54]), "+f"(d[55]), "+f"(d[56]), "+f"(d[57]), "+f"(d[58]), "+f"(d[59]), "+f"(d[60]), "+f"(d[61]), "+f"(d[62]), "+f"(d[63])
                 : "r"(hi.x), "r"(hi.y), "r"(lo.x), "r"(lo.y), "l"(db), "r"(acc));
}
template <int V> struct Int { __device__ constexpr operator int() const { return V; } };
__device__ __forceinline__ void sts4(uint32_t a, const uint32_t* v) { asm volatile("st.shared.v4.u32 [%0], {%1,%2,%3,%4};" ::"r"(a), "r"(v[0]), "r"(v[1]), "r"(v[2]), "r"(v[3]) : "memory"); }
__device__ __forceinline__ uint32_t lds1(uint32_t a) { uint32_t v; asm volatile("ld.shared.u32 %0, [%1];" : "=r"(v) : "r"(a) : "memory"); return v; }
__device__ __forceinline__ uint32_t lds1v(uint32_t a) { uint32_t v; asm volatile("ld.volatile.shared.u32 %0, [%1];" : "=r"(v) : "r"(a) : "memory"); return v; }
__device__ __forceinline__ uint4 lds4(uint32_t a) { uint4 v; asm volatile("ld.shared.v4.u32 {%0,%1,%2,%3}, [%4];" : "=r"(v.x), "=r"(v.y), "=r"(v.z), "=r"(v.w) : "r"(a) : "memory"); return v; }
__device__ __forceinline__ uint4 ldx(uint32_t a) {
    uint4 v;
    asm volatile("ld.shared.v2.u32 {%0,%1}, [%4];\nld.shared.v2.u32 {%2,%3}, [%4+128];" : "=r"(v.x), "=r"(v.y), "=r"(v.z), "=r"(v.w) : "r"(a) : "memory");
    return v;
}
__device__ __forceinline__ void cv_store(unsigned char* p, uint4 x, uint4 y) {
    asm volatile("st.relaxed.gpu.global.v2.u32 [%0], {%1,%2};" ::"l"(p), "r"(add2(x.x, __byte_perm(y.x, y.y, 0x5410))), "r"(add2(x.y, __byte_perm(y.z, y.w, 0x5410))) : "memory");
    asm volatile("st.relaxed.gpu.global.v2.u32 [%0], {%1,%2};" ::"l"(p + 128), "r"(add2(x.z, __byte_perm(y.x, y.y, 0x7632))), "r"(add2(x.w, __byte_perm(y.z, y.w, 0x7632))) : "memory");
}
__device__ __forceinline__ int usw(int ch) { return ch ^ ((ch >> 3) & 1); }
__global__ void __launch_bounds__(CV_THREADS, 1) conv_kernel(int layer, const uint4* __restrict__ piv, const float4* __restrict__ sum, const bf16* __restrict__ x1T,
                                                             bf16* __restrict__ dst, const uint4* __restrict__ tap, const __grid_constant__ CUtensorMap tmOut) {
    extern __shared__ __align__(1024) unsigned char sm[];
    SPAN(3 + 4 * layer, 0);
    bf16* Us = reinterpret_cast<bf16*>(sm + CV_SM_U);
    bf16* Xs = reinterpret_cast<bf16*>(sm + CV_SM_X);
#define CV_IDX int tid; asm volatile("mov.u32 %0, %tid.x;" : "=r"(tid)); const int lane = tid & 31, warp = __shfl_sync(~0u, tid >> 5, 0);
    const int d0 = blockIdx.x * CV_CPB, tile = blockIdx.x; (void)tile;
    const uint32_t cnt = smem_u32(sm + CV_SM_CNT);
    struct Lc { uint32_t a4, a8, uc, ud, y, e4, en, sp, ss; int go; };
    auto lane_consts = [&](int lane, int c) {
        const int mat = lane >> 3, r = lane & 7, g = lane >> 2, ti = lane & 3, e = g - 2 * ti;
        const int j2 = 13 + (r ^ 1) + 8 * (mat >> 1), j3 = j2 + 2, i0 = 8 * (mat & 1);
        const uint32_t sb = smem_u32(sm), oc = sb + usw(16 * (mat >> 1) + 2 * r + (mat & 1)) * 16;
        const Lc l = {sb + CV_SM_B + c * BX_LEN + ((j2 & 1) ? BX_3 + (4 * j2 + i0 + 84) * 2 : BX_5 + (4 * j2 + i0 + 80) * 2),
                      sb + CV_SM_B + c * BX_LEN + ((j3 & 1) ? BX_7 : BX_9) + (8 * j3 + i0 + 136) * 2,
                      oc + CV_SM_U + (c * ULEN + UPADF) * 2, sb + CV_SM_U + (c * ULEN + UPADF) * 2 + usw(16 * mat + 2 * r + 2) * 16, oc + CV_SM_Y + c * 8192,
                      sb + CV_SM_T + c * TAPB + TAPE + (307 + 2 * g - ti) * 4, sb + CV_SM_T + c * TAPB + (528 + e) * 4,
                      e == -5 ? 0x4410u : e == -4 ? 0x1044u : 0x4444u, e == 3 ? 0x4410u : e == 4 ? 0x1044u : 0x4444u,
                      c * XCP * 2 + (lane >> 4) * 256 + (lane & 15) * 8};
        asm volatile("st.shared.u32 [%0], %1;" ::"r"(sb + CV_SM_CNT + 120), "r"(l.y ^ l.a4 ^ l.a8 ^ l.uc ^ l.ud ^ l.e4 ^ l.en ^ l.sp ^ l.ss ^ l.go) : "memory");
        return l;
    };
    unsigned char* const dq = reinterpret_cast<unsigned char*>(dst + (size_t)d0 * XCP);
    auto far = [&](auto T0_, const auto& seq, const Lc& lc, int c, int lane, const uint2 (&f)[20], uint32_t kk) {
        constexpr int T0 = T0_, T1 = T0 + 6, TC = T0 > 7 ? T0 : 7, NS = sizeof(seq) / sizeof(seq[0]), PD = T0 > 7 ? CV_PDH : CV_PDF;
        uint32_t bq[28], yw[4], yz[4], P, S;
        uint4 xv, yv;
        asm("prmt.b32 %0, %1, 0, %2;" : "=r"(P) : "r"(kk), "r"(lc.sp));
        asm("prmt.b32 %0, %1, 0, %2;" : "=r"(S) : "r"(kk), "r"(lc.ss));
#pragma unroll
        for (int k = 0; 2 * k < T1 - TC + 4; k++) ldsm_x4(bq + 4 * k, lc.uc + (TC - 8) * 256 + 512 * k);
#pragma unroll
        for (int k = 0; 4 * k < T1 - TC; k++) ldsm_x4(bq + 20 + 4 * k, lc.ud + (TC - 8) * 256 + 1024 * k);
        CST(3);
        mbar_wait(cnt + 8 * c, 0);
        mbar_wait(cnt + 40, 0);
        CST(4);
        float acc[6][4] = {};
        uint32_t a[PD + 1][4];
#pragma unroll
        for (int i = -PD; i < NS + 3; i++) {
            if (i + PD < NS) ldsm_x4_t(a[(i + PD) % (PD + 1)], seq[i + PD] < 32 ? lc.a4 + (seq[i + PD] - 2) * 128 : lc.a8 + (seq[i + PD] - 34) * 256);
            if (i < 0) continue;
#pragma unroll
            for (int T = T0; T < T1; T++) {
                if (i >= NS) break;
                const int ee = seq[i] < 32 ? 2 * T - 6 - seq[i] : T + 35 - seq[i];
                if (i == 0 && T >= TC) mma_bf16(acc[T - T0], P, 0u, S, P, bq[2 * (T - TC)], bq[2 * (T - TC) + 1]);
                if (i == 1 && T >= TC) mma_bf16_k8(acc[T - T0], 0u, S, bq[20 + T - TC]);
                if (i == (T >= TC ? 2 : 0)) mma_bf16(acc[T - T0], f[19].x, 0u, f[19].y, f[19].x, bq[2 * (T - TC + 4)], bq[2 * (T - TC + 4) + 1]);
                if (seq[i] < 32 ? ee >= 0 && ee <= 9 : ee >= 10) mma_bf16(acc[T - T0], a[i % (PD + 1)][0], a[i % (PD + 1)][1], a[i % (PD + 1)][2], a[i % (PD + 1)][3], f[ee].x, f[ee].y);
            }
#pragma unroll
            for (int k = 0; k < 3; k++) {
                const int o = 256 * T0 + 512 * k;
                auto at = [&](int d) { return i - d >= 0 && i - d < NS && seq[i - d < 0 ? 0 : i - d < NS ? i - d : 0] == 2 * T0 + 4 * k - 4; };
                if (at(CV_D2)) {
                    cv_store(dq + lc.go + o, xv, yv);
                    if (layer > 19 - 2 * k) __trap();
                }
                if (at(-2)) { ldsm_x4_t(yw, lc.y + o); ldsm_x4_t(yz, lc.y + 3584 + o); }
                if (at(1)) {
#pragma unroll
                    for (int q = 0; q < 4; q++) yw[q] = add2(add2(yw[q], yz[q]), pack2(acc[2 * k + (q >> 1)][2 * (q & 1)], acc[2 * k + (q >> 1)][2 * (q & 1) + 1]));
                    stsm_x4_t(lc.y + o, yw[0], yw[1], yw[2], yw[3]);
                    xv = ldx(smem_u32(Xs) + lc.go + o);
                    __syncwarp();
                    yv = lds4(smem_u32(sm + CV_SM_Y) + c * 8192 + o + usw(lane) * 16);
                    if (layer > 20 - 2 * k) __trap();
                    if (k == 2) CST(6);
                }
            }
        }
    };
    TSTAMP1X(9, 256);
    if (threadIdx.x >= 256) {
        if (threadIdx.x < 288 && elect()) {
            mbar_init(cnt + 48, 1);
            asm volatile("fence.mbarrier_init.release.cluster;" ::: "memory");
            bulk_load(smem_u32(sm + CV_SM_T), tap + d0 * (TAPB / 16), CV_CPB * TAPB, cnt + 48);
            mbar_expect_tx(cnt + 48, CV_CPB * TAPB);
        }
        CV_IDX
        const int wgu = (warp >> 2) & 1, g = lane >> 2, ti = lane & 3;
        CST(1);
        if (warp > 8 && elect()) {
            if (warp < 15) mbar_init(cnt + 8 * (warp - 9), warp == 14 ? 8 : 4);
            else if (layer) prefetch_tmap(&tmOut);
        }
        if (warp < 13 && lane < 17 - (warp == 12)) {
            const int off = warp == 12 ? CV_SM_U : CV_SM_B + (warp == 11 ? BX_7 : (warp - 8) * BX_3), str = warp == 12 ? ULEN * 2 : BX_LEN;
#pragma unroll
            for (int c = 0; c < CV_CPB; c++) *reinterpret_cast<uint4*>(sm + off + c * str + 16 * lane) = make_uint4(0, 0, 0, 0);
        }
        fence_async_smem();
        asm volatile("bar.arrive 3, 512;" ::: "memory");
        asm volatile("bar.sync 1, 256;" ::: "memory");
        TSTAMP1X(10, 256);
        asm volatile("setmaxnreg.inc.sync.aligned.u32 168;");
        const uint32_t Tc = smem_u32(sm + CV_SM_T) + (16 + 128 * (warp & 2) + 8 * (warp & 1) + g - 2 * ti) * 4;
        uint2 fa[8][2], fn[8][2];
        auto near_taps = [&](uint2 (&f)[8][2], int c) {
#pragma unroll
            for (int m = 0; m < 16; m++) f[m >> 1][m & 1] = make_uint2(lds1v(Tc + c * TAPB + 64 * (m >> 1) - 32 * (m & 1)), lds1v(Tc + c * TAPB + 64 * (m >> 1) - 32 * (m & 1) + 512));
        };
        CST(6);
        mbar_wait(cnt + 48, 0);
        TSTAMP1X(11, 256); CST(5);
        near_taps(fa, 3 * wgu);
        near_taps(fn, 2 - wgu);
        const int hc = wgu ? warp & 3 : 4;
        const Lc lc = lane_consts(lane, hc);
        TSTAMP1X(12, 256); CST(0);
        uint32_t ya = smem_u32(sm + CV_SM_Y) + wgu * 8192 + (warp & 2) * 2048 + usw(2 * lane + (warp & 1)) * 16;
        uint64_t db = make_desc(smem_u32(Us + wgu * ULEN + UPADF), 16, 256, 3);
        if (wgu) { asm volatile("bar.sync 6, 384;" ::: "memory"); fence_async_smem(); }
        int c = wgu;
        auto chain = [&](const uint2 (&f)[8][2], auto&& meanwhile) {
            float acc[64];
            asm volatile("bar.sync %0, %1;" ::"r"(c ? 4 + wgu : 2), "r"(c ? 256 : 384) : "memory");
            TSTAMPC(1 + 3 * c);
            if (c < 2) CST(7);
            if (c == 0) fence_async_smem();
            wgmma_fence();
#pragma unroll
            for (int m = 0; m < 8; m++) {
                wgmma_rs128(acc, f[m][0], f[m][1], db - (uint64_t)(2 * m), m);
                if (m == CV_HAND && c < 4) asm volatile("bar.arrive %0, 256;" ::"r"(5 - wgu) : "memory");
            }
            wgmma_commit();
            asm volatile("griddepcontrol.launch_dependents;" ::: "memory");
            TSTAMPC(2 + 3 * c); CST(13 + (c >> 1));
            meanwhile();
            wgmma_wait<0>();
            TSTAMPC(3 + 3 * c); CST(10 + (c >> 1));
            uint32_t w[16];
#pragma unroll
            for (int j = 0; j < 16; j++) w[j] = j ? pack2(acc[4 * j] + acc[4 * j - 2], acc[4 * j + 1] + acc[4 * j - 1]) : pack2(acc[0], acc[1]);
#pragma unroll
            for (int j = 0; j < 16; j += 4) stsm_x4_t(ya + 256 * j, w[j], w[j + 1], w[j + 2], w[j + 3]);
            __syncwarp();
            if (lane == 0) mbar_arrive(cnt + 8 * c);
            c += 2; ya += 16384; db += ULEN / 4;
        };
        const uint32_t e4 = lc.e4, e8 = e4 + 428 - 4 * g;
        uint2 fl[4];
        uint32_t kk;
#pragma unroll 1
        for (;;) {
            if (c != 1) chain(fa, [&] {
                if (c == 3 || warp + c == 12) {
#pragma unroll
                    for (int k = 0; k < 19; k++) (k < 16 ? fn[(k >> 1) & 7][k & 1] : fl[k & 3]) = make_uint2(lds1(k < 10 ? e4 + 32 * k + 16 : e8 + 32 * k - 304), lds1(k < 10 ? e4 + 32 * k : e8 + 32 * k - 320));
                    fl[3] = make_uint2(lds1(lc.en), lds1(lc.en - 32));
                    kk = lds1(smem_u32(sm + CV_SM_T) + TAPB * hc + TAPE + 1672);
                }
            });
            if (c > 4) break;
            if (c == 2) { asm volatile("bar.sync 7, 384;" ::: "memory"); fence_async_smem(); }
            chain(fn, [&] { if (c == 2) near_taps(fa, 4); });
        }
        TSTAMP1X(6, 256); CST(2);
        if (wgu || warp == 8) {
            constexpr int seq[29] = {5, 6, 32, 7, 33, 8, 34, 9, 35, 10, 36, 11, 12, 13, 14, 15, 16, 17, 37, 18, 38, 19, 20, 21, 39, 22, 40, 23, 24};
            uint2 f[20];
#pragma unroll
            for (int k = 0; k < 20; k++) f[k] = k < 16 ? fn[(k >> 1) & 7][k & 1] : fl[k & 3];
            far(Int<10>(), seq, lc, hc, lane, f, kk);
        }
    } else {
        asm volatile("setmaxnreg.dec.sync.aligned.u32 88;");
        CV_IDX
        CST(5);
        const uint4* ppv = piv + tid;
        const float4* psv = sum + tid;
        const uint2* pxv = reinterpret_cast<const uint2*>(x1T + (size_t)d0 * XCP) + (tid >> 4) * 32 + (tid & 15);
        asm volatile("st.shared.u64 [%0], %1;" ::"r"(smem_u32(sm + CV_SM_O) + tid * 16), "l"((uint64_t)ppv ^ (uint64_t)psv ^ (uint64_t)pxv) : "memory");
        const int tc = (0x04302100 >> (4 * warp)) & 7;
        const Lc lc = lane_consts(lane, tc);
        pdl_sync();
        SPAN(3 + 4 * layer, 1);
        TSTAMP(0); CST(0);
        if (tid == 0) TSTAMPC(0);
        if (threadIdx.x == 0) { GSTAMP(g_tim, 15); }
        float4 sv[4];
        uint4 pv;
#pragma unroll
        for (int k = 0; k < 4; k++)
            asm volatile(CV_LD ".v4.f32 {%0,%1,%2,%3}, [%4];" : "=f"(sv[k].x), "=f"(sv[k].y), "=f"(sv[k].z), "=f"(sv[k].w) : "l"(psv + 256 * k) : "memory");
        asm volatile(CV_LD ".v4.u32 {%0,%1,%2,%3}, [%4];" : "=r"(pv.x), "=r"(pv.y), "=r"(pv.z), "=r"(pv.w) : "l"(ppv) : "memory");
        uint2 xe[CV_CPB], xo[CV_CPB];
#pragma unroll
        for (int c = 0; c < CV_NL; c++) {
            asm volatile(CV_LD ".v2.u32 {%0,%1}, [%2];" : "=r"(xe[c].x), "=r"(xe[c].y) : "l"(pxv + c * (XCP / 4)) : "memory");
            asm volatile(CV_LD ".v2.u32 {%0,%1}, [%2];" : "=r"(xo[c].x), "=r"(xo[c].y) : "l"(pxv + c * (XCP / 4) + 16) : "memory");
        }
#define CV_XD 300
#define CV_XW 0
        if (warp == CV_XW) {
            if (elect()) {
                const uint32_t c0 = clock();
                mbar_init(cnt + 56, 1);
                asm volatile("fence.mbarrier_init.release.cluster;" ::: "memory");
                mbar_expect_tx(cnt + 56, CV_CPB * 4096);
                while (clock() - c0 < CV_XD) ;
#pragma unroll
                for (int c = CV_NL; c < CV_CPB + CV_NL; c++) bulk_load(smem_u32(Xs + (c % CV_CPB) * XLEN), x1T + (size_t)(d0 + c % CV_CPB) * XCP, 4096, cnt + 56);
            }
            __syncwarp();
            CST(15);
        }
        constexpr float idm = 1.0f / DM;
        uint32_t mw[4];
        float rs[8];
#pragma unroll
        for (int k = 0; k < 4; k++) {
            const uint32_t pw = k == 0 ? pv.x : k == 1 ? pv.y : k == 2 ? pv.z : pv.w;
            mw[k] = pack2(fmaf(sv[k].x, idm, __uint_as_float(pw << 16)), fmaf(sv[k].z, idm, __uint_as_float(pw & 0xffff0000u)));
            uint32_t vr;
            asm("cvt.rn.relu.bf16x2.f32 %0, %1, %2;" : "=r"(vr) : "f"(fmaf(sv[k].z * -idm, sv[k].z, sv[k].w) * idm), "f"(fmaf(sv[k].x * -idm, sv[k].x, sv[k].y) * idm));
            const uint32_t ve = pack2(__uint_as_float(vr << 16) + 1e-5f, __uint_as_float(vr & 0xffff0000u) + 1e-5f);
            const uint32_t sd = pack2(sqrt_apx(__uint_as_float(ve << 16)), sqrt_apx(__uint_as_float(ve & 0xffff0000u)));
            rs[2 * k] = rcp_apx(__uint_as_float(sd << 16)); rs[2 * k + 1] = rcp_apx(__uint_as_float(sd & 0xffff0000u));
        }
        if (rs[0] != 123.f) TSTAMP(13);
        const uint32_t ua = smem_u32(Us) + usw(tid + UPADF / 8) * 16;
        uint32_t uw[CV_CPB][4];
#pragma unroll
        for (int c = 0; c < CV_CPB; c++) {
            if (c == CV_NL) {
                if (warp == CV_XW) { mbar_wait(cnt + 56, 0); CST(7); }
                asm volatile("bar.sync 10, 256;" ::: "memory");
            }
            if (c == 1 || c == 2) {
#pragma unroll
                for (int k = c; k < (c == 1 ? 2 : CV_CPB); k++) {
 const uint4 v = ldx(smem_u32(Xs + k * XLEN) + (tid >> 4) * 256 + (tid & 15) * 8); xe[k] = make_uint2(v.x, v.y); xo[k] = make_uint2(v.z, v.w); }
            }
            const uint32_t e0 = sub2(xe[c].x, mw[0]), e1 = sub2(xe[c].y, mw[1]), o0 = sub2(xo[c].x, mw[2]), o1 = sub2(xo[c].y, mw[3]);
            uw[c][0] = pack2(__uint_as_float(e0 << 16) * rs[0], __uint_as_float(o0 << 16) * rs[4]); uw[c][1] = pack2(__uint_as_float(e0 & 0xffff0000u) * rs[1], __uint_as_float(o0 & 0xffff0000u) * rs[5]);
            uw[c][2] = pack2(__uint_as_float(e1 << 16) * rs[2], __uint_as_float(o1 << 16) * rs[6]); uw[c][3] = pack2(__uint_as_float(e1 & 0xffff0000u) * rs[3], __uint_as_float(o1 & 0xffff0000u) * rs[7]);
            asm volatile("st.shared.v4.u32 [%0], {%1,%2,%3,%4};" ::"r"(ua + c * ULEN * 2), "r"(uw[c][0]), "r"(uw[c][1]), "r"(uw[c][2]), "r"(uw[c][3]) : "memory");
            if (c < 2) {
                asm volatile("bar.arrive %0, 384;" ::"r"(2 + 4 * c) : "memory");
                if (layer > 29 - c) __trap();
                CST(11 + c);
            }
        }
        asm volatile("bar.arrive 7, 384;" ::: "memory");
        asm volatile("bar.sync 3, 512;" ::: "memory");
        TSTAMP(1); CST(1);
        {
            auto box = [&](auto c0, auto c1, int chunk, int cb, bool full) {
                const uint32_t ea = smem_u32(Us + cb * ULEN) + usw(chunk + UPADF / 8 + (lane ? 1 : -1)) * 16, bx = smem_u32(sm + CV_SM_B + cb * BX_LEN) + chunk * 16;
                uint32_t lo[CV_CPB][4], hi[CV_CPB][2];
#pragma unroll
                for (int c = c0; c < c1; c++) {
                    lo[c][0] = 0;
#pragma unroll
                    for (int k = 1; k < 4; k++) lo[c][k] = __shfl_up_sync(~0u, uw[c][k], 1);
#pragma unroll
                    for (int k = 0; k < 2; k++) hi[c][k] = __shfl_down_sync(~0u, uw[c][k], 1);
                }
#pragma unroll
                for (int c = c0; c < c1; c++)
                    asm volatile("{\n.reg .pred p, q;\nsetp.eq.s32 p, %7, 0;\nsetp.eq.s32 q, %7, 31;\n@p ld.shared.v4.u32 {%0,%1,%2,%3}, [%6];\n@q ld.shared.v2.u32 {%4,%5}, [%6];\n}"
                                 : "+r"(lo[c][0]), "+r"(lo[c][1]), "+r"(lo[c][2]), "+r"(lo[c][3]), "+r"(hi[c][0]), "+r"(hi[c][1]) : "r"(ea + c * ULEN * 2), "r"(lane) : "memory");
#pragma unroll
                for (int c = c0; c < c1; c++) {
                    const uint32_t e[9] = {lo[c][1], lo[c][2], lo[c][3], uw[c][0], uw[c][1], uw[c][2], uw[c][3], hi[c][0], hi[c][1]};
                    uint32_t o[8], p[8], t[7], b3[5], b5[7];
#pragma unroll
                    for (int i = 0; i < 8; i++) { o[i] = __byte_perm(e[i], e[i + 1], 0x5432); p[i] = add2(e[i], o[i]); }
#pragma unroll
                    for (int i = 0; i < 5; i++) b3[i] = add2(o[i], p[i + 1]);
                    sts4(bx + c * BX_LEN + BX_3 + 160, b3);
#pragma unroll
                    for (int i = 1; i < 7; i++) { t[i] = add2(p[i], p[i + 1]); b5[i] = add2(t[i], e[i + 2]); }
                    sts4(bx + c * BX_LEN + BX_5 + 160, b5 + 2);
                    if (full) {
#pragma unroll
                        for (int i = 1; i < 5; i++) { b3[i] = add2(b3[i], t[i + 2]); t[i] = add2(t[i], b5[i + 2]); }
                        sts4(bx + c * BX_LEN + BX_7 + 272, b3 + 1);
                        sts4(bx + c * BX_LEN + BX_9 + 272, t + 1);
                    }
                }
            };
            auto reload = [&](int c, uint32_t a) { const uint4 v = lds4(a); uw[c][0] = v.x; uw[c][1] = v.y; uw[c][2] = v.z; uw[c][3] = v.w; };
            if (warp >= 6) {
#pragma unroll
                for (int c = 0; c < 3; c++) reload(c, ua - 1024 + (c + 2) * ULEN * 2);
            }
            if (warp >= 4) {
#pragma unroll
                for (int c = 3; c < 5; c++) reload(c, ua - 2048 + c * ULEN * 2);
            }
            box(Int<0>(), Int<3>(), warp < 6 ? tid : tid - 64, warp < 6 ? 0 : 2, warp < 4);
            if (warp >= 4) box(Int<3>(), Int<5>(), tid - 128, 0, true);
            else if (tid >= 128 - CV_CPB) {
                const int c = 127 - tid;
                const uint2 v = *reinterpret_cast<const uint2*>(Us + c * ULEN + UPADF);
                const float s1 = __uint_as_float(v.x << 16), s2 = s1 + __uint_as_float(v.x & 0xffff0000u), s3 = s2 + __uint_as_float(v.y << 16), s4 = s3 + __uint_as_float(v.y & 0xffff0000u);
                unsigned char* bc = sm + CV_SM_B + c * BX_LEN;
                *reinterpret_cast<uint32_t*>(bc + BX_5 + 156) = pack2(s1, s2);
                *reinterpret_cast<uint2*>(bc + BX_7 + 264) = make_uint2(v.x << 16, pack2(s2, s3));
                *reinterpret_cast<uint2*>(bc + BX_9 + 264) = make_uint2(pack2(s1, s2), pack2(s3, s4));
            }
        }
        __syncwarp();
        if (lane == 0) mbar_arrive(cnt + 40);
        TSTAMP(2); CST(2);
        if (layer && blockIdx.x == 0 && tid == 224) g_epoch = ld_epoch();
        __syncwarp();
        if ((0x6e >> warp) & 1) {
            constexpr int seq[16] = {0, 1, 2, 3, 4, 5, 6, 32, 7, 8, 9, 33, 10, 34, 11, 12};
            uint2 f[20];
            mbar_wait(cnt, 0);
            const uint32_t e8 = lc.e4 + 428 - (lane & 28);
#pragma unroll
            for (int k = 0; k < 13; k++) f[k] = make_uint2(lds1(k < 10 ? lc.e4 + 32 * k + 16 : e8 + 32 * k - 304), lds1(k < 10 ? lc.e4 + 32 * k : e8 + 32 * k - 320));
            f[19] = make_uint2(lds1(lc.en), lds1(lc.en - 32));
            far(Int<4>(), seq, lc, tc, lane, f, lds1(smem_u32(sm + CV_SM_T) + TAPB * tc + TAPE + 1672));
        }
    }
    {
        CV_IDX
        if ((0xc91 >> warp) & 1) {
            const int c = __popc(0xc91 & ((1 << warp) - 1));
            uint4 xv[2], yv[2];
#pragma unroll
            for (int k = 0; k < 2; k++) xv[k] = ldx(smem_u32(Xs + c * XLEN) + 512 * k + (lane >> 4) * 256 + (lane & 15) * 8);
            const uint32_t u0 = lds1(smem_u32(Us + c * ULEN) + (lane == 31 ? UPADF * 2 : 0));
            mbar_wait(cnt + 8 * c, 0);
#pragma unroll
            for (int k = 0; k < 2; k++) yv[k] = lds4(smem_u32(sm + CV_SM_Y) + c * 8192 + 512 * k + usw(lane) * 16);
            const uint4 yz = lds4(smem_u32(sm + CV_SM_Y) + c * 8192 + 4096 + usw(lane) * 16);
            const float kk = __uint_as_float(lds1(smem_u32(sm + CV_SM_T) + TAPB * c + TAPE + 1272) << 16);
            yv[1].x = add2(yv[1].x, yz.x); yv[1].y = add2(yv[1].y, yz.y); yv[1].z = add2(yv[1].z, yz.z);
            yv[1].w = pack2(fmaf(kk, __uint_as_float(u0 << 16), __uint_as_float(yv[1].w << 16) + __uint_as_float(yz.w << 16)),
                            fmaf(kk, __uint_as_float(u0 << 16) + __uint_as_float(u0 & 0xffff0000u), __uint_as_float(yv[1].w & 0xffff0000u) + __uint_as_float(yz.w & 0xffff0000u)));
#pragma unroll
            for (int k = 0; k < 2; k++) cv_store(dq + c * XCP * 2 + (lane >> 4) * 256 + (lane & 15) * 8 + 512 * k, xv[k], yv[k]);
        }
        TSTAMP(4); CST(8);
        if (layer == 1) {
            const int rb = (blockIdx.x >> 3) + (warp & 8) * 2, cg = blockIdx.x & 7, ch = (tid >> 3) & 31;
            const bf16* src = dst + (size_t)(cg * 80 + ch) * XCP + rb * 64 + (tid & 7) * 8;
            uint32_t v[3][4];
            __syncthreads();
            if (warp & 8) { const uint32_t c0 = clock(); while (clock() - c0 < 300) ; }
            uint32_t todo = (warp & 4) ? 3 : 7;
#pragma unroll 1
            for (int it = 0; it < SPIN_MAX; it++) {
#pragma unroll
                for (int k = 0; k < 3; k++)
                    if (todo >> k & 1)
                        asm volatile("ld.relaxed.gpu.global.v4.u32 {%0,%1,%2,%3}, [%4];" : "=r"(v[k][0]), "=r"(v[k][1]), "=r"(v[k][2]), "=r"(v[k][3]) : "l"(src + k * (32 * XCP)) : "memory");
#pragma unroll
                for (int k = 0; k < 3; k++)
                    if ((todo >> k & 1) && v[k][0] != ~0u && v[k][1] != ~0u && v[k][2] != ~0u && v[k][3] != ~0u) {
                        *reinterpret_cast<uint4*>(sm + (32 * k + ch) * 272 + ((tid & 7) + (warp & 8)) * 16) = make_uint4(v[k][0], v[k][1], v[k][2], v[k][3]);
                        todo ^= 1u << k;
                    }
                if (!todo) break;
                __nanosleep(CV_SLEEP);
            }
            __syncwarp();
            asm volatile("bar.sync %0, 256;" ::"r"(8 + (warp >> 3)) : "memory");
            uint32_t w[12];
#pragma unroll
            for (int k = 0; k < 3; k++) ldsm_x4(&w[4 * k], smem_u32(sm) + min(32 * k + lane, 79) * 272 + warp * 16);
            const uint32_t ot = smem_u32(sm + CV_SM_O) + warp * 1280, oa = ot + (lane & 7) * 160 + (lane >> 3) * 16;
            stsm_x4_t(oa, w[0], w[1], w[2], w[3]);
            stsm_x4_t(oa + 64, w[4], w[5], w[6], w[7]);
            asm volatile("stmatrix.sync.aligned.m8n8.x2.trans.shared.b16 [%0], {%1,%2};" ::"r"(oa + 128), "r"(w[8]), "r"(w[9]) : "memory");
            fence_async_smem();
            __syncwarp();
            if (lane == 0) {
                asm volatile("cp.async.bulk.tensor.3d.global.shared::cta.bulk_group [%0, {%1, %2, %3}], [%4];" ::"l"(&tmOut), "r"(cg * 80), "r"((rb >> 1) * 64 + 8 * (warp & 7)), "r"(rb & 1), "r"(ot) : "memory");
                asm volatile("cp.async.bulk.commit_group;" ::: "memory");
                asm volatile("cp.async.bulk.wait_group.read 0;" ::: "memory");
            }
        }
    }
    TSTAMP(3); CST(9); CST_END;
    GSTAMP(g_tim, 14);
    SPAN(3 + 4 * layer, 3);
}

template <int TA, int TB>
__device__ __forceinline__ void wgmma_n240(float (&d)[120], uint64_t da, uint64_t db, int acc) {
    asm volatile("{\n.reg .pred p;\nsetp.ne.b32 p, %124, 0;\nwgmma.mma_async.sync.aligned.m64n240k16.f32.bf16.bf16 {%0,%1,%2,%3,%4,%5,%6,%7,%8,%9,%10,%11,%12,%13,%14,%15,%16,%17,%18,%19,%20,%21,%22,%23,%24,%25,%26,%27,%28,%29,%30,%31,%32,%33,%34,%35,%36,%37,%38,%39,%40,%41,%42,%43,%44,%45,%46,%47,%48,%49,%50,%51,%52,%53,%54,%55,%56,%57,%58,%59,%60,%61,%62,%63,%64,%65,%66,%67,%68,%69,%70,%71,%72,%73,%74,%75,%76,%77,%78,%79,%80,%81,%82,%83,%84,%85,%86,%87,%88,%89,%90,%91,%92,%93,%94,%95,%96,%97,%98,%99,%100,%101,%102,%103,%104,%105,%106,%107,%108,%109,%110,%111,%112,%113,%114,%115,%116,%117,%118,%119}, %120, %121, p, 1, 1, %122, %123;\n}"
                 : "+f"(d[0]), "+f"(d[1]), "+f"(d[2]), "+f"(d[3]), "+f"(d[4]), "+f"(d[5]), "+f"(d[6]), "+f"(d[7]), "+f"(d[8]), "+f"(d[9]), "+f"(d[10]), "+f"(d[11]), "+f"(d[12]), "+f"(d[13]), "+f"(d[14]), "+f"(d[15]), "+f"(d[16]), "+f"(d[17]), "+f"(d[18]), "+f"(d[19]), "+f"(d[20]), "+f"(d[21]), "+f"(d[22]), "+f"(d[23]), "+f"(d[24]), "+f"(d[25]), "+f"(d[26]), "+f"(d[27]), "+f"(d[28]), "+f"(d[29]), "+f"(d[30]), "+f"(d[31]), "+f"(d[32]), "+f"(d[33]), "+f"(d[34]), "+f"(d[35]), "+f"(d[36]), "+f"(d[37]), "+f"(d[38]), "+f"(d[39]), "+f"(d[40]), "+f"(d[41]), "+f"(d[42]), "+f"(d[43]), "+f"(d[44]), "+f"(d[45]), "+f"(d[46]), "+f"(d[47]), "+f"(d[48]), "+f"(d[49]), "+f"(d[50]), "+f"(d[51]), "+f"(d[52]), "+f"(d[53]), "+f"(d[54]), "+f"(d[55]), "+f"(d[56]), "+f"(d[57]), "+f"(d[58]), "+f"(d[59]), "+f"(d[60]), "+f"(d[61]), "+f"(d[62]), "+f"(d[63]), "+f"(d[64]), "+f"(d[65]), "+f"(d[66]), "+f"(d[67]), "+f"(d[68]), "+f"(d[69]), "+f"(d[70]), "+f"(d[71]), "+f"(d[72]), "+f"(d[73]), "+f"(d[74]), "+f"(d[75]), "+f"(d[76]), "+f"(d[77]), "+f"(d[78]), "+f"(d[79]), "+f"(d[80]), "+f"(d[81]), "+f"(d[82]), "+f"(d[83]), "+f"(d[84]), "+f"(d[85]), "+f"(d[86]), "+f"(d[87]), "+f"(d[88]), "+f"(d[89]), "+f"(d[90]), "+f"(d[91]), "+f"(d[92]), "+f"(d[93]), "+f"(d[94]), "+f"(d[95]), "+f"(d[96]), "+f"(d[97]), "+f"(d[98]), "+f"(d[99]), "+f"(d[100]), "+f"(d[101]), "+f"(d[102]), "+f"(d[103]), "+f"(d[104]), "+f"(d[105]), "+f"(d[106]), "+f"(d[107]), "+f"(d[108]), "+f"(d[109]), "+f"(d[110]), "+f"(d[111]), "+f"(d[112]), "+f"(d[113]), "+f"(d[114]), "+f"(d[115]), "+f"(d[116]), "+f"(d[117]), "+f"(d[118]), "+f"(d[119])
                 : "l"(da), "l"(db), "n"(TA), "n"(TB), "r"(acc));
}

__device__ __forceinline__ void wgmma_n80(float (&d)[40], uint64_t da, uint64_t db, int acc) {
    asm volatile("{\n.reg .pred p;\nsetp.ne.b32 p, %42, 0;\nwgmma.mma_async.sync.aligned.m64n80k16.f32.bf16.bf16 {%0,%1,%2,%3,%4,%5,%6,%7,%8,%9,%10,%11,%12,%13,%14,%15,%16,%17,%18,%19,%20,%21,%22,%23,%24,%25,%26,%27,%28,%29,%30,%31,%32,%33,%34,%35,%36,%37,%38,%39}, %40, %41, p, 1, 1, 0, 1;\n}"
                 : "+f"(d[0]), "+f"(d[1]), "+f"(d[2]), "+f"(d[3]), "+f"(d[4]), "+f"(d[5]), "+f"(d[6]), "+f"(d[7]), "+f"(d[8]), "+f"(d[9]), "+f"(d[10]), "+f"(d[11]), "+f"(d[12]), "+f"(d[13]), "+f"(d[14]), "+f"(d[15]), "+f"(d[16]), "+f"(d[17]), "+f"(d[18]), "+f"(d[19]), "+f"(d[20]), "+f"(d[21]), "+f"(d[22]), "+f"(d[23]), "+f"(d[24]), "+f"(d[25]), "+f"(d[26]), "+f"(d[27]), "+f"(d[28]), "+f"(d[29]), "+f"(d[30]), "+f"(d[31]), "+f"(d[32]), "+f"(d[33]), "+f"(d[34]), "+f"(d[35]), "+f"(d[36]), "+f"(d[37]), "+f"(d[38]), "+f"(d[39])
                 : "l"(da), "l"(db), "r"(acc));
}

constexpr int A1_THREADS = 384;
constexpr int A1_NST = 4;
#define A1_SKEW 8
constexpr int A1_STAGE = 16384 + WQ_STAGE;
constexpr int A1_KVP = 336;
constexpr int A1_SM_KV = 2 * A1_STAGE;
constexpr int A1_SM_BAR = A1_NST * A1_STAGE;
constexpr int A1_SM_RS = A1_SM_BAR + 512;
constexpr int A1_SM_W0 = A1_SM_BAR + 3072, A1_SM_W3 = A1_SM_BAR - 3 * WOB, A1_SM_A1 = 2 * WOB, A1_SM_A0 = A1_SM_A1 + 61440;
constexpr int A1_SM_XA = A1_SM_W0 + 2 * WOB, A1_SM_XB = A1_SM_XA + 2048;
constexpr int A1_SMEM = A1_SM_W0 + 3 * WOB + CST_EXTRA;
static_assert(A1_SM_W3 >= A1_SM_KV + 144 * A1_KVP && A1_SM_W3 % 512 == 0 && A1_SM_A1 % 1024 == 0 && A1_SM_A0 <= A1_SM_KV && A1_SM_A0 + 61440 <= A1_SM_W3 && A1_SMEM <= 232448, "layout");
__device__ __forceinline__ constexpr uint32_t wo_off(int h) { return h * WOB + (h < 3 ? A1_SM_W0 : h < 6 ? A1_SM_W3 - 3 * WOB : -6 * WOB); }
#define A1_FRED "red.relaxed.gpu.global.add.u32"
#define A1_FLD "ld.acquire.gpu.global.u32"
#define ST_SLEEP 20
#define ST_SLEEP0 300
#define WO_LATE bar_done
#define A1_P0 2
#define A1_PW (kb - 2)
#define A1_FSPIN SPIN_MAX
#define A1_FSLEEP 40
#define YT_LAYER 1
#define WOT 352
#define A1_WOAT 6

template <int L>
__device__ __forceinline__ void a1_mainloop(float (&acc)[120], uint32_t sbase, uint32_t bars, int wg, int tile) {
    constexpr int layer = L; (void)layer;
    const uint64_t da0 = L ? make_desc(sbase + wg * 8192, 8192, 1024, 1) : make_desc(sbase + wg * 8192, 16, 1024, 1), db0 = make_desc(sbase + 16384, 1024, 256, 3);
#pragma unroll 1
    for (int t = 0;; t++) {
        const int st = t % A1_NST;
        mbar_wait(bars + 8 * st, (t / A1_NST) & 1);
        if (t == A1_SKEW && wg == 0) mbar_wait(bars + 160, 0);
        TSTAMP3(1 + t);
        if (t == 0) CSA(0);
        wgmma_fence();
#pragma unroll
        for (int kk = 0; kk < 4; kk++) wgmma_n240<L, 1>(acc, da0 + (uint32_t)(st * (A1_STAGE / 16) + kk * (L ? 128 : 2)), db0 + (uint32_t)(st * (A1_STAGE / 16) + (kk >> 1) * (WQ_STAGE / 32) + (kk & 1) * 32), kk ? 1 : t);
        wgmma_commit();
        if (t == 9) break;
        if (t == A1_SKEW - 1 && wg == 0) wgmma_wait<0>(); else wgmma_wait<1>();
        if (t > 0 && (threadIdx.x & 127) == 0) {
            if (t != A1_SKEW || wg) mbar_arrive(bars + 8 * (A1_NST + (t - 1) % A1_NST));
            if (t == A1_SKEW - 1 && wg == 0) mbar_arrive(bars + 8 * (A1_NST + t % A1_NST));
        }
    }
}

template <bool MAP>
__global__ void __launch_bounds__(A1_THREADS, 1) a1_kernel(const int layer, const bf16* __restrict__ x0, const unsigned char* __restrict__ wo,
                                                           float2* __restrict__ rsum, uint4* __restrict__ of, const __grid_constant__ CUtensorMap tmX,
                                                           const __grid_constant__ CUtensorMap tmR, const __grid_constant__ CUtensorMap tmX1, const __grid_constant__ TileTab tab) {
    extern __shared__ __align__(1024) unsigned char stg[];
    const uint32_t sbase = smem_u32(stg);
    const uint32_t bars = sbase + A1_SM_BAR;
    const uint32_t bar_stat = bars + 64, bar_kv = bars + 72, bar_rd = bars + 168;
    const uint32_t bar_wo = bars + 208, bar_done = bars + 216, bar_pv = bars + 224, bar_kvf = bars + 232, bar_f2 = bars + 248, bar_e2 = bars + 384, que = bars + 448;
    const int tid = threadIdx.x;
    const int w = __shfl_sync(~0u, tid >> 5, 0), wg = w >> 2;
    uint32_t smid;
    asm volatile("mov.u32 %0, %smid;" : "=r"(smid));
    const uint4 tv = tab.e[(MAP ? smid : blockIdx.x) + (tid & (smid >> 12))];
    const bool one = elect();
    if (w == 8) {
        if (one) {
            prefetch_tmap(&tmX);
#pragma unroll
            for (int i = 0; i < A1_NST; i++) mbar_init(bars + 8 * i, 1);
            asm volatile("fence.mbarrier_init.release.cluster;" ::: "memory");
        }
        __syncwarp();
        asm volatile("bar.arrive 0, 384;" ::: "memory");
    }
    const uint32_t tz = __shfl_sync(~0u, tv.z, 0);
    const int tile = tz >> 24, mb = tz & 15, hg = (tz >> 8) & 7;
    struct { const unsigned char* wq; int kb0, layer; } te = {(const unsigned char*)(((uint64_t)__shfl_sync(~0u, tv.y, 0) << 32) | __shfl_sync(~0u, tv.x, 0)), (int)(tz >> 16) & 7, (int)tz & 16};
    float2* rst = reinterpret_cast<float2*>(stg + A1_SM_RS) + 8;
    auto issue_w = [&](int it) { bulk_load(sbase + (it % A1_NST) * A1_STAGE + 16384, te.wq + it * WQ_STAGE, WQ_STAGE, bars + 8 * (it % A1_NST)); };
    auto issue_x = [&](int it, int kb) {
        asm volatile("cp.async.bulk.tensor.5d.shared::cluster.global.mbarrier::complete_tx::bytes [%0], [%1, {%3, %3, %3, %4, %5}], [%2];"
                     ::"r"(sbase + (it % A1_NST) * A1_STAGE), "l"(&tmX), "r"(bars + 8 * (it % A1_NST)), "r"(0), "r"(mb), "r"(kb) : "memory");
    };
    if (w == 8 && tile < 128) {
        if (one) {
#define PW asm volatile("griddepcontrol.wait;" ::: "memory");
            if (te.layer) { issue_w(0); PW issue_x(0, te.kb0); issue_x(1, te.kb0 + 1); }
            else { issue_x(0, te.kb0); issue_x(1, te.kb0 + 1); PW issue_w(0); }
            issue_w(1);
#pragma unroll
            for (int i = 0; i < A1_NST; i++) mbar_expect_tx(bars + 8 * i, A1_STAGE);
            asm volatile("griddepcontrol.launch_dependents;" ::: "memory");
#pragma unroll
            for (int kb = 2; kb < A1_P0; kb++) { issue_x(kb, te.kb0 + kb); issue_w(kb); }
            DBGC(34); DBGV(33, smid); DBGV(40, t_entry); DBGV(30, t_a); DBGV(31, t_b); DBGV(32, t_c); DBGV(38, t_d); DBGV(39, t_e);
        }
    }
    if (tile >= 128) { sm_idle(layer); return; }
    if (wg == 2) {
        if (w != 8) {
            if (tid == 320) {
                prefetch_tmap(&tmR); prefetch_tmap(&tmX1);
                uint32_t ns;
                asm volatile("mov.u32 %0, %nsmid;" : "=r"(ns));
                if (MAP && ns != 132) __trap();
            }
            if (w == 11 && layer == 0 && elect()) {
                mbar_init(bars + 240, 1);
                asm volatile("fence.mbarrier_init.release.cluster;" ::: "memory");
                mbar_expect_tx(bars + 240, 20480);
                bulk_load(sbase + A1_SM_W0, x0 + (size_t)(mb * 128 + hg * 16) * DM, 20480, bars + 240);
            }
            __syncwarp();
            asm volatile("bar.sync 0, 384;" ::: "memory");
        }
        if (w == 9) {
            asm volatile("bar.arrive 3, 64;" ::: "memory");
            if (layer == 0) pdl_sync();
            float4 a[2] = {};
#pragma unroll
            for (int k = 0; k < 10; k++)
#pragma unroll
                for (int h = 0; h < 2; h++) {
                    const int c4 = min(tid - 288 + 32 * h, 59);
                    const float4 v = __ldcg(reinterpret_cast<const float4*>(g_csp + k * 1920 + hg * 80) + c4 + (c4 / 20) * 140);
                    a[h].x += v.x; a[h].y += v.y; a[h].z += v.z; a[h].w += v.w;
                }
#pragma unroll
            for (int h = 0; h < 2; h++)
#pragma unroll
                for (int k = 0; k < 4; k++) {
                    const float c = 0.5f * (k == 0 ? a[h].x : k == 1 ? a[h].y : k == 2 ? a[h].z : a[h].w), c1 = c - rbf(c), c2 = c1 - rbf(c1);
                    *reinterpret_cast<uint4*>(stg + A1_SM_XB + (4 * min(tid - 288 + 32 * h, 59) + k) * 16) = make_uint4(pack2(c, c1), pack2(c2, 0.f), 0u, 0u);
                }
            fence_async_smem();
            __syncwarp();
            if (tid == 288) mbar_arrive(bar_stat);
            CSA(1);
            uint4* pre = of + (mb * 8 + hg) * 1280 + (tid - 288);
#pragma unroll 1
            for (int k = 0; k < 5 + 5 * layer; k++) {
#pragma unroll
                for (int i = 0; i < 8; i++) asm volatile("st.global.v4.u32 [%0], {%1,%1,%1,%1};" ::"l"(pre + 32 * i), "r"(~0u) : "memory");
                pre += k < 5 ? 256 : XCP / 8;
                if (k == 4) {
                    CSA(2);
                    asm volatile("fence.acq_rel.gpu;" ::: "memory");
                    asm volatile("fence.proxy.async.global;" ::: "memory");
                    __syncwarp();
                    if (tid == 288) mbar_arrive(bar_done);
                    CSA(3);
                    pre = reinterpret_cast<uint4*>(g_yT) + tile * (5 * XCP / 8) + (tid - 288);
                }
            }
            TSTAMP1T(9, 288);
        } else if (w == 8) {
            asm volatile("bar.sync 3, 64;" ::: "memory");
            if (elect()) {
#pragma unroll 1
                for (int kb = A1_P0; kb < 10; kb++) {
                    if (kb < A1_NST) mbar_wait(bars + 8 * A1_PW, 0);
                    else {
                        mbar_wait(bars + 8 * (A1_NST + kb % A1_NST), ((kb / A1_NST) - 1) & 1);
                        if (layer && kb < 9) mbar_wait(bar_rd + 8 * (kb - A1_NST), 0);
                        mbar_expect_tx(bars + 8 * (kb % A1_NST), A1_STAGE);
                    }
                    issue_x(kb, kb < 5 ? kb + te.kb0 : kb - te.kb0); issue_w(kb);
                    if (kb == (layer ? A1_WOAT : 9)) {
                        if (!layer) mbar_wait(bar_rd + 32, 0);
                        mbar_expect_tx(bar_wo, 8 * WOB);
                        bulk_load(sbase + A1_SM_W0, wo + hg * 8 * WOB, 2 * WOB, bar_wo);
                    }
                }
                TSTAMP1T(6, 256);
                mbar_wait(bars + 8 * (A1_NST + 3), 1);
                bulk_load(sbase + A1_SM_W3, wo + (hg * 8 + 3) * WOB, 3 * WOB, bar_wo);
            }
            __syncwarp();
        } else {
            const int j = tid - 320;
            const uint32_t tag = ld_epoch();
            if (tid == 352) sm_started(layer);
            const int ch = j & 7, kg = (j >> 3) & 3;
            const unsigned char* src = stg + (layer ? (j >> 5) * 8192 + (hg & 3) * 2048 : A1_SM_W0 + (j >> 2) * 1280);
            const int of0 = layer ? kg * 128 + ((ch ^ kg) << 4) : (j & 7) << 4, ofx = layer ? 576 : 64, ofy = layer ? 1024 : 128;
            float s[8], q[8], p0[8];
#pragma unroll
            for (int i = 0; i < 8; i++) { s[i] = 0.f; q[i] = 0.f; }
#pragma unroll 1
            for (int it = 0; it < 5; it++) {
                uint4 v[4];
                mbar_wait(layer ? bars + 8 * (it % A1_NST) : bars + 240, layer * it / A1_NST);
#pragma unroll
                for (int k = 0; k < 4; k++) v[k] = *reinterpret_cast<const uint4*>(src + (layer ? (it % A1_NST) * A1_STAGE : it * 256) + (k & 1 ? of0 ^ ofx : of0) + (k >> 1) * ofy);
                if (it == 0) {
                    const uint4 pv = *reinterpret_cast<const uint4*>(src + (layer ? ch << 4 : 0));
                    const uint32_t w[4] = {pv.x, pv.y, pv.z, pv.w};
#pragma unroll
                    for (int i = 0; i < 4; i++) { p0[2 * i] = __uint_as_float((layer ? w[i] : w[0]) << 16); p0[2 * i + 1] = __uint_as_float(layer ? w[i] & 0xffff0000u : w[0] << 16); }
                }
                asm volatile("" :: "r"(v[0].x), "r"(v[1].x), "r"(v[2].x), "r"(v[3].x), "f"(p0[0]) : "memory");
                __syncwarp();
                if ((tid & 31) == 0) mbar_arrive(bar_rd + 8 * it);
#pragma unroll
                for (int k = 0; k < 4; k++) {
                    const uint32_t w[4] = {v[k].x, v[k].y, v[k].z, v[k].w};
#pragma unroll
                    for (int i = 0; i < 4; i++) {
                        const float a = __uint_as_float(w[i] << 16) - p0[2 * i], b = __uint_as_float(w[i] & 0xffff0000u) - p0[2 * i + 1];
                        s[2 * i] += a; s[2 * i + 1] += b; q[2 * i] = fmaf(a, a, q[2 * i]); q[2 * i + 1] = fmaf(b, b, q[2 * i + 1]);
                    }
                }
            }
            float o[4];
            int row;
            if (layer == 0) {
                float s0 = ((s[0] + s[1]) + (s[2] + s[3])) + ((s[4] + s[5]) + (s[6] + s[7])), q0 = ((q[0] + q[1]) + (q[2] + q[3])) + ((q[4] + q[5]) + (q[6] + q[7]));
#pragma unroll
                for (int o = 1; o <= 2; o <<= 1) { s0 += __shfl_xor_sync(~0u, s0, o); q0 += __shfl_xor_sync(~0u, q0, o); }
                if ((j & 3) == 0) {
                    const float d = s0 * (1.0f / DM);
                    const uint32_t ms = pack2(p0[0] + d, sqrt_apx(rbf(rbf(fmaxf(fmaf(-d, d, q0 * (1.0f / DM)), 0.f)) + 1e-5f)));
                    asm volatile("st.global.cg.u64 [%0], %1;" ::"l"(g_rstat + mb * 128 + (j & 4) * 16 + hg * 8 + (j >> 3)), "l"(tagw(ms, tag)) : "memory");
                    g_piv[mb * 128 + hg * 16 + ((j >> 2) & 8) + (j & 4) + ((j >> 3) & 3)] = __ushort_as_bfloat16((unsigned short)ms);
                }
                ulonglong2 v;
#pragma unroll 1
                for (int it = 0; it < SPIN_MAX; it++) {
                    v = ld_tag2(reinterpret_cast<const ulonglong2*>(g_rstat + mb * 128) + j);
                    if (tag_ok(v, tag)) break;
                    __nanosleep(100);
                }
                o[0] = __uint_as_float((uint32_t)v.x << 16); o[1] = rcp_apx(__uint_as_float((uint32_t)v.x & 0xffff0000u));
                o[2] = __uint_as_float((uint32_t)v.y << 16); o[3] = rcp_apx(__uint_as_float((uint32_t)v.y & 0xffff0000u));
                row = 2 * j;
            } else {
#pragma unroll
                for (int i = 0; i < 4; i++) {
                    const bool up = kg & 2;
                    const float ss = __shfl_xor_sync(~0u, up ? s[i] : s[i + 4], 16), qq = __shfl_xor_sync(~0u, up ? q[i] : q[i + 4], 16);
                    s[i] = (up ? s[i + 4] : s[i]) + ss; q[i] = (up ? q[i + 4] : q[i]) + qq; p0[i] = up ? p0[i + 4] : p0[i];
                }
#pragma unroll
                for (int i = 0; i < 2; i++) {
                    const bool up = kg & 1;
                    const float ss = __shfl_xor_sync(~0u, up ? s[i] : s[i + 2], 8), qq = __shfl_xor_sync(~0u, up ? q[i] : q[i + 2], 8);
                    s[i] = (up ? s[i + 2] : s[i]) + ss; q[i] = (up ? q[i + 2] : q[i]) + qq; p0[i] = up ? p0[i + 2] : p0[i];
                }
                uint4* gp = g_halo + 86016 + mb * 512 + j;
                const float d0 = s[0] * (1.0f / 80.0f), d1 = s[1] * (1.0f / 80.0f);
                asm volatile("st.relaxed.gpu.global.v4.f32 [%0], {%1,%2,%3,%4};" ::"l"(gp + hg * 64), "f"(p0[0] + d0), "f"(fmaxf(fmaf(-d0, s[0], q[0]), 0.f)), "f"(p0[1] + d1), "f"(fmaxf(fmaf(-d1, s[1], q[1]), 0.f)) : "memory");
                __nanosleep(ST_SLEEP0);
                uint32_t pw[8][4], todo = 0xff;
#pragma unroll 1
                for (int it = 0; it < SPIN_MAX; it++) {
#pragma unroll
                    for (int k = 0; k < 8; k++)
                        if (todo >> k & 1) asm volatile("ld.relaxed.gpu.global.v4.u32 {%0,%1,%2,%3}, [%4];" : "=r"(pw[k][0]), "=r"(pw[k][1]), "=r"(pw[k][2]), "=r"(pw[k][3]) : "l"(gp + k * 64) : "memory");
#pragma unroll
                    for (int k = 0; k < 8; k++)
                        if (__all_sync(~0u, pw[k][0] != ~0u && pw[k][1] != ~0u && pw[k][2] != ~0u && pw[k][3] != ~0u)) todo &= ~(1u << k);
                    if (!todo) break;
                    __nanosleep(ST_SLEEP);
                }
#pragma unroll
                for (int r = 0; r < 2; r++) {
                    float mean = 0.f, m2 = 0.f;
#pragma unroll
                    for (int k = 0; k < 8; k++) mean += __uint_as_float(pw[k][2 * r]);
                    mean *= 0.125f;
#pragma unroll
                    for (int k = 0; k < 8; k++) {
                        const float dm = __uint_as_float(pw[k][2 * r]) - mean;
                        m2 += fmaf(80.0f * dm, dm, __uint_as_float(pw[k][2 * r + 1]));
                    }
                    o[2 * r] = rbf(mean);
                    o[2 * r + 1] = rcp_apx(rbf(sqrt_apx(rbf(rbf(m2 * (1.0f / DM)) + 1e-5f))));
                }
                row = (j >> 5) * 64 + (j & 7) * 8 + ((j >> 3) & 3) * 2;
                if (hg == 0) *reinterpret_cast<uint32_t*>(g_piv + SEQ + mb * 128 + 2 * (row & 60) + 4 * (row >> 6) + (row & 3)) = __byte_perm(__float_as_uint(o[0]), __float_as_uint(o[2]), 0x7632);
            }
#pragma unroll
            for (int r = 0; r < 2; r++)
                *reinterpret_cast<uint4*>(stg + A1_SM_XA + (row + r) * 16) = make_uint4(__byte_perm(__float_as_uint(-o[2 * r]), 0, 0x3232), __float_as_uint(-o[2 * r]) >> 16, 0u, 0u);
            *reinterpret_cast<float4*>(rst + row + (row >> 6) * 8) = make_float4(o[0], o[1], o[2], o[3]);
            fence_async_smem();
            TSTAMP1T(7, 320); CSA(1);
            if (tid == 320) DBGC(44);
            __syncwarp();
            if ((tid & 31) == 0) mbar_arrive(bar_stat);
        }
        CSA(4); CSA_END;
        if (tid == 320) DBGCAL(0);
        if (tid == WOT) {
            mbar_wait(WO_LATE, 0);
            mbar_wait(bar_done, 0);
            bulk_load(sbase, wo + (hg * 8 + 6) * WOB, 2 * WOB, bar_wo);
            bulk_load(sbase + A1_SM_W0 + 2 * WOB, wo + (hg * 8 + 2) * WOB, WOB, bar_wo);
        }
        __syncwarp();
#define FWA 11
#define FWB 10
        if (w == FWA || w == FWB) {
            const int cw = w == FWB;
            const uint32_t* fl = reinterpret_cast<const uint32_t*>(rsum + 2 * SEQ) + (((layer * 16 + mb) * 2 + cw) * 8 + (tid & 7)) * FSTR;
            const unsigned char* src = reinterpret_cast<const unsigned char*>(of) + mb * 163840 + cw * 10240 + (tid & 7) * 20480;
            const uint32_t sl = sbase + (cw ? A1_SM_A1 : A1_SM_A0);
            mbar_wait(cw ? bar_done : bar_kvf, 0);
            if ((tid & 31) == 0) {
                mbar_expect_tx(bar_f2 + 64 * cw + 64, 10240);
                tma_load_3d(sl + 51200, &tmR, layer ? 0 : hg * 80, layer ? hg * 80 : mb * 64, layer ? mb * 2 + cw : cw, bar_f2 + 64 * cw + 64);
            }
            __syncwarp();
            uint32_t pend = 0xffu & ~(1u << hg), v = 0;
            const uint32_t bo = wo_off((tid & 7) + ((tid & 7) < hg)) >> 4, lt = (1u << (tid & 31)) - 1;
#pragma unroll 1
            for (int it = 0; pend && it < 2 * SPIN_MAX; it++) {
                if (v != 4 && (pend >> (tid & 31) & 1)) asm volatile(A1_FLD " %0, [%1];" : "=r"(v) : "l"(fl) : "memory");
                uint32_t fr;
                asm volatile("{\n.reg .pred p;\nmbarrier.test_wait.parity.shared::cta.b64 p, [%1], 0;\nselp.b32 %0, 1, 0, p;\n}" : "=r"(fr) : "r"(bar_e2 + 16 * cw + (tid & 1) * 8) : "memory");
                fr = __ballot_sync(~0u, fr);
                uint32_t m = __ballot_sync(~0u, v == 4 || it >= A1_FSPIN) & pend;
                const int q = 8 - __popc(pend) + __popc(m & lt);
                m &= __ballot_sync(~0u, q < ((fr & 2) ? 8 : (fr & 1) ? 7 : 5));
                pend ^= m;
                if (m >> (tid & 31) & 1) DBGC(12 + cw * 8 + (tid & 7));
                if (!m) __nanosleep(A1_FSLEEP);
                else asm volatile("fence.proxy.async.global;" ::: "memory");
                if (m >> (tid & 31) & 1) {
                    bulk_load(q == 7 && !cw ? sbase + A1_SM_W0 : sl + (q < 6 ? q : q - 6) * 10240, src, 10240, bar_f2 + 64 * cw + 8 * q);
                    asm volatile("st.shared.u32 [%0], %1;" ::"r"(que + 32 * cw + 4 * q), "r"(bo) : "memory");
                    mbar_expect_tx(bar_f2 + 64 * cw + 8 * q, 10240);
                    DBGC(44 + cw * 8 + q);
                }
                __syncwarp();
            }
        }
    } else {
        if (one) {
#pragma unroll 1
            for (uint32_t c = tab.cnt[w], b = bars + 56 * w; c; c >>= 4, b += 8)
                if (c & 15) mbar_init(b, c & 15);
            asm volatile("fence.mbarrier_init.release.cluster;" ::: "memory");
        }
        __syncwarp();
        asm volatile("bar.sync 0, 384;" ::: "memory");
        SPAN(1 + 4 * layer, 0);
        constexpr int on = 1;
        float acc[120];
        const int lane = tid & 31, warp = w & 7, g = lane >> 2, t = lane & 3;
        if (on) {
            SPAN(1 + 4 * layer, 1);
            TSTAMP1(0);
            if (threadIdx.x == 0) { GSTAMP(g_tim1, 15); }
            TSTAMP3(0);
            if (tid == 0) TSTAMP2(0);
            TSTAMP4(0);
            if (tid == 0) DBGC(60);
            if (layer == 0) a1_mainloop<0>(acc, sbase, bars, wg, tile); else a1_mainloop<1>(acc, sbase, bars, wg, tile);
            uint32_t ok;
            asm volatile("{\n.reg .pred p;\nmbarrier.test_wait.parity.shared::cta.b64 p, [%1], 0;\nselp.b32 %0, 1, 0, p;\n}" : "=r"(ok) : "r"(bar_stat) : "memory");
            if (tid == 128 && !ok) mbar_arrive(bars + 160);
            __syncwarp();
            mbar_wait(bar_stat, 0);
            wgmma_fence();
            wgmma_n240<0, 0>(acc, make_desc(sbase + A1_SM_XA + wg * 1024, 0, 128, 0), make_desc(sbase + A1_SM_XB, 0, 128, 0), 1);
            wgmma_commit();
            if (tid == 128 && ok) mbar_arrive(bars + 160);
            mbar_wait(bars + 8 * (A1_NST + 3), 1);
        }
        const float2* rw = rst + 16 * warp + 8 * wg;
        const float rb0 = rw[g + 8].y, ra = rw[g].y * 0.22360679774997896f, rb = rb0 * 0.22360679774997896f;
        wgmma_wait<0>();
        if ((tid & 127) == 0) mbar_arrive(bar_done);
        TSTAMP1(2); CSA(1);
        TSTAMP1T(13, 224);
        if ((tid & 127) == 0) DBGC(62 - wg);
        uint32_t f[2][30];
#pragma unroll
        for (int j = 10; j < 30; j++) f[1][j] = pack2(acc[4 * j + 2], acc[4 * j + 3]);
        if ((warp & 3) == 3) {
            uint4* hout = g_halo + (((layer * 16 + mb) * 8 + hg) * 2 + wg) * 168;
#pragma unroll
            for (int j = 0; j < 20; j += 4)
                asm volatile("st.relaxed.gpu.global.v4.u32 [%0], {%1,%2,%3,%4};" ::"l"(hout + 8 * j + lane), "r"(f[1][10 + j]), "r"(f[1][11 + j]), "r"(f[1][12 + j]), "r"(f[1][13 + j]) : "memory");
            if (t == 0) asm volatile("st.relaxed.gpu.global.f32 [%0], %1;" ::"l"(reinterpret_cast<float*>(hout + 160) + g), "f"(rb0) : "memory");
        }
        TSTAMP1T(12, 224);
        const uint32_t kvw = sbase + A1_SM_KV + (16 * warp + 8 * wg) * A1_KVP;
        const uint32_t mrow = kvw + (lane & 7) * A1_KVP + (lane >> 3) * 16;
#pragma unroll
        for (int j = 0; j < 20; j += 4) stsm_x4(mrow + 16 * A1_KVP + 16 * j, f[1][10 + j], f[1][11 + j], f[1][12 + j], f[1][13 + j]);
        __syncwarp();
        if (lane == 0 && (warp & 3) != 3) mbar_arrive(bar_kv + 8 * (warp + 1));
#pragma unroll
        for (int j = 0; j < 30; j++) f[0][j] = pack2(acc[4 * j], acc[4 * j + 1]);
        stsm_x4(mrow + 8 * A1_KVP + 160, f[0][20], f[0][21], f[0][22], f[0][23]);
        stsm_x4(mrow + 8 * A1_KVP + 224, f[0][24], f[0][25], f[0][26], f[0][27]);
        asm volatile("stmatrix.sync.aligned.m8n8.x2.shared.b16 [%0], {%1,%2};" ::"r"(mrow + 8 * A1_KVP + 288), "r"(f[0][28]), "r"(f[0][29]) : "memory");
#pragma unroll
        for (int j = 0; j < 10; j++) f[1][j] = pack2(acc[4 * j + 2], acc[4 * j + 3]);
        __syncwarp();
        uint32_t vb[10][2], vp[12], kp[12];
#pragma unroll
        for (int j = 0; j < 10; j += 2) ldsm_x4_t(&vb[j][0], kvw + (8 + (lane & 15)) * A1_KVP + 160 + (lane >> 4) * 16 + 16 * j);
        const bool up0 = 2 * t > g, up1 = 2 * t + 1 > g, edge = (mb | (warp & 3)) == 0;
        float rk[4];
        auto above = [&]() {
            mbar_wait(bar_kv + 8 * warp, 0);
#pragma unroll
            for (int j = 0; j < 12; j += 4) ldsm_x4(&kp[j], mrow + 16 * j);
            rk[0] = rw[2 * t - (up0 ? 8 : 0)].y; rk[1] = rw[2 * t + 1 - (up1 ? 8 : 0)].y;
#pragma unroll
            for (int j = 0; j < 12; j += 4) ldsm_x4_t(&vp[j], mrow + 160 + 16 * j - (j == 8 ? (lane & 16) * 2 : 0));
            __syncwarp();
            if (lane == 0) mbar_arrive(bar_kvf);
        };
        auto halo = [&]() {
            if (lane == 0) mbar_arrive(bar_kvf);
            const uint4* hin = g_halo + (((layer * 16 + mb - 1) * 8 + hg) * 2 + wg) * 168;
            uint32_t hv[22] = {};
            rk[0] = rw[2 * t].y; rk[1] = rw[2 * t + 1].y;
            if (mb > 0) {
#pragma unroll 1
                for (int it = 0; it < SPIN_MAX; it++) {
#pragma unroll
                    for (int k = 0; k < 20; k += 4)
                        asm volatile("ld.relaxed.gpu.global.v4.u32 {%0,%1,%2,%3}, [%4];" : "=r"(hv[k]), "=r"(hv[k + 1]), "=r"(hv[k + 2]), "=r"(hv[k + 3]) : "l"(hin + 8 * k + lane) : "memory");
                    asm volatile("ld.relaxed.gpu.global.v2.u32 {%0,%1}, [%2];" : "=r"(hv[20]), "=r"(hv[21]) : "l"(reinterpret_cast<const uint2*>(hin + 160) + t) : "memory");
                    uint32_t m = max(hv[20], hv[21]);
#pragma unroll
                    for (int k = 0; k < 20; k += 2) m = __vimax3_u32(m, hv[k], hv[k + 1]);
                    if (!__any_sync(~0u, m == ~0u)) break;
                }
            }
            if (lane == 0) DBGC(52 - 16 * wg);
#pragma unroll
            for (int j = 0; j < 10; j++) {
                kp[j] = hv[j];
                asm volatile("movmatrix.sync.aligned.m8n8.trans.b16 %0, %1;" : "=r"(vp[j]) : "r"(hv[10 + j]));
            }
            if (up0) rk[0] = __uint_as_float(hv[20]);
            if (up1) rk[1] = __uint_as_float(hv[21]);
        };
        rk[2] = rw[2 * t + (up0 ? 0 : 8)].y; rk[3] = rw[2 * t + 1 + (up1 ? 0 : 8)].y;
        uint32_t qs[4][2];
#pragma unroll
        for (int h = 0; h < 4; h++) {
            qs[h][0] = (t >> 1) == (h & 1) ? f[0][5 * (h >> 1) + 2] : 0u; qs[h][1] = (t >> 1) == (h & 1) ? f[1][5 * (h >> 1) + 2] : 0u;
            asm volatile("" : "+r"(qs[h][0]), "+r"(qs[h][1]));
        }
#pragma unroll
        for (int j = 0; j < 10; j++) asm volatile("" : "+r"(f[0][j]), "+r"(f[1][j]), "+r"(f[0][10 + j]));
        if (warp & 3) above(); else if (wg) halo();
        TSTAMP1T(10, 64); CSA(2);
        if (warp && !wg) mbar_wait(bars + 416 + 8 * warp, 0);
        CSA(3);
        float sc[4][3][4];
#pragma unroll
        for (int h = 0; h < 4; h++) {
            const int jb = 5 * (h >> 1) + 3 * (h & 1), js = 5 * (h >> 1) + 2;
#pragma unroll
            for (int nt = 1; nt < 3; nt++) {
#pragma unroll
                for (int e = 0; e < 4; e++) sc[h][nt][e] = 0.f;
                mma_bf16(sc[h][nt], f[0][jb], f[1][jb], f[0][jb + 1], f[1][jb + 1], f[nt - 1][10 + jb], f[nt - 1][11 + jb]);
                mma_bf16_k8(sc[h][nt], qs[h][0], qs[h][1], f[nt - 1][10 + js]);
            }
        }
        if (warp == 0) halo();
        TSTAMP1(8); CSA(4);
#pragma unroll
        for (int h = 0; h < 4; h++) {
            const int jb = 5 * (h >> 1) + 3 * (h & 1), js = 5 * (h >> 1) + 2;
#pragma unroll
            for (int e = 0; e < 4; e++) sc[h][0][e] = 0.f;
            mma_bf16(sc[h][0], f[0][jb], f[1][jb], f[0][jb + 1], f[1][jb + 1], kp[jb], kp[jb + 1]);
            mma_bf16_k8(sc[h][0], qs[h][0], qs[h][1], kp[js]);
        }
        TSTAMP1T(3, 64);
        float p[4][4], sum[4][2];
        uint32_t lg[4][2], mx[4];
        const float rl[4] = {rk[0] * ra, rk[1] * ra, rk[2] * rb, rk[3] * rb};
        auto max2 = [](uint32_t a, uint32_t b) { uint32_t r; asm("max.bf16x2 %0, %1, %2;" : "=r"(r) : "r"(a), "r"(b)); return r; };
#pragma unroll
        for (int h = 0; h < 4; h++) {
            lg[h][0] = pack2((up0 ? sc[h][0][0] : sc[h][1][0]) * rl[0], (up0 ? sc[h][1][2] : sc[h][2][2]) * rl[2]);
            lg[h][1] = pack2((up1 ? sc[h][0][1] : sc[h][1][1]) * rl[1], (up1 ? sc[h][1][3] : sc[h][2][3]) * rl[3]);
            if (edge) {
                if (up0) lg[h][0] = __byte_perm(lg[h][0], 0xce6eu, 0x3254);
                if (up1) lg[h][1] = __byte_perm(lg[h][1], 0xce6eu, 0x3254);
            }
            mx[h] = max2(lg[h][0], lg[h][1]);
        }
#pragma unroll
        for (int o = 1; o <= 2; o <<= 1)
#pragma unroll
            for (int h = 0; h < 4; h++) mx[h] = max2(mx[h], __shfl_xor_sync(~0u, mx[h], o));
#pragma unroll
        for (int h = 0; h < 4; h++)
#pragma unroll
            for (int r = 0; r < 2; r++) {
                const float m = __uint_as_float(r ? mx[h] & 0xffff0000u : mx[h] << 16);
#pragma unroll
                for (int e = 0; e < 2; e++)
                    asm("ex2.approx.ftz.f32 %0, %1;" : "=f"(p[h][2 * r + e]) : "f"((__uint_as_float(r ? lg[h][e] & 0xffff0000u : lg[h][e] << 16) - m) * 1.4426950408889634f));
                sum[h][r] = p[h][2 * r] + p[h][2 * r + 1];
            }
#pragma unroll
        for (int o = 1; o <= 2; o <<= 1)
#pragma unroll
            for (int h = 0; h < 4; h++)
#pragma unroll
                for (int r = 0; r < 2; r++) sum[h][r] += __shfl_xor_sync(~0u, sum[h][r], o);
        TSTAMP1T(5, 64); CSA(5);
        const uint32_t mu = (up0 ? 0xffffu : 0u) | (up1 ? 0xffff0000u : 0u);
        uint32_t ob[10][2];
#pragma unroll
        for (int P = 0; P < 2; P++) {
            float os[2][4];
#pragma unroll
            for (int e = 0; e < 2; e++) {
                const int h = 2 * P + e;
                const float i0 = rcp_apx(sum[h][0]), i1 = rcp_apx(sum[h][1]);
                const uint32_t w0 = pack2(p[h][0] * rk[0] * i0, p[h][1] * rk[1] * i0), w1 = pack2(p[h][2] * rk[2] * i1, p[h][3] * rk[3] * i1);
#pragma unroll
                for (int dt = 0; dt < 3; dt++) {
                    const int j = 5 * P + (dt < 2 ? 3 * e + dt : 2);
                    float o[4] = {0.f, 0.f, 0.f, 0.f};
                    mma_bf16(o, w0 & ~mu, w1 & mu, 0u, w1 & ~mu, vb[j][0], vb[j][1]);
                    mma_bf16_k8(o, w0 & mu, 0u, vp[j]);
                    if (dt < 2) { ob[j][0] = pack2(o[0], o[1]); ob[j][1] = pack2(o[2], o[3]); }
                    else { os[e][0] = o[0]; os[e][1] = o[1]; os[e][2] = o[2]; os[e][3] = o[3]; }
                }
            }
#pragma unroll
            for (int k = 0; k < 4; k++) os[0][k] = t < 2 ? os[0][k] : os[1][k];
            ob[5 * P + 2][0] = pack2(os[0][0], os[0][1]); ob[5 * P + 2][1] = pack2(os[0][2], os[0][3]);
        }
        const uint32_t sl = sbase + (wg ? A1_SM_A1 : A1_SM_A0);
        const uint32_t o0 = (warp & 3) * 2048 + g * 64 + ((t ^ (g >> 1)) << 4), o1 = 8192 + (warp & 3) * 512 + g * 32 + ((t ^ ((g >> 2) << 1)) << 3);
        CSA(15);
        mbar_wait(bar_done, 0);
        if (wg == 0) mbar_wait(bar_kvf, 0);
#pragma unroll
        for (int h = 0; h < 2; h++) {
            asm volatile("st.shared.v4.u32 [%0], {%1,%2,%3,%4};" ::"r"(sl + o0 + h * 1024), "r"(ob[0][h]), "r"(ob[1][h]), "r"(ob[2][h]), "r"(ob[3][h]) : "memory");
            asm volatile("st.shared.v4.u32 [%0], {%1,%2,%3,%4};" ::"r"(sl + o0 + h * 1024 + 512), "r"(ob[4][h]), "r"(ob[5][h]), "r"(ob[6][h]), "r"(ob[7][h]) : "memory");
            asm volatile("st.shared.v2.u32 [%0], {%1,%2};" ::"r"(sl + o1 + h * 256), "r"(ob[8][h]), "r"(ob[9][h]) : "memory");
        }
        if (wg && lane == 0) mbar_arrive(bars + 384 + 8 * warp);
        fence_async_smem();
        __syncwarp();
        TSTAMP1T(4, 64); CSA(6);
        TSTAMP1(1);
        TSTAMP2(1);
        const unsigned char* ot = reinterpret_cast<const unsigned char*>(of) + mb * 163840 + wg * 10240;
        if (lane == 0) {
            asm volatile("cp.async.bulk.global.shared::cta.bulk_group [%0], [%1], 2048;" ::"l"(ot + hg * 20480 + (warp & 3) * 2048), "r"(sl + (warp & 3) * 2048) : "memory");
            asm volatile("cp.async.bulk.global.shared::cta.bulk_group [%0], [%1], 512;" ::"l"(ot + hg * 20480 + 8192 + (warp & 3) * 512), "r"(sl + 8192 + (warp & 3) * 512) : "memory");
            asm volatile("cp.async.bulk.commit_group;" ::: "memory");
            if (wg == 0) mbar_arrive(bar_pv);
            asm volatile("cp.async.bulk.wait_group 0;" ::: "memory");
            asm volatile(A1_FRED " [%0], 1;" ::"l"(reinterpret_cast<uint32_t*>(rsum + 2 * SEQ) + (((layer * 16 + mb) * 2 + wg) * 8 + hg) * FSTR) : "memory");
            DBGC(4 + warp);
        }
        TSTAMP4(11); CSA(7);
        float ac2[40];
        const uint64_t db0 = make_desc(sbase, 1024, 256, 3), db1 = make_desc(sbase + 10240, 512, 256, 3), da0 = make_desc(sl, 16, 1024, 2), da1 = make_desc(sl + 8192, 16, 256, 3);
        const uint32_t o7 = wg ? 640 : (A1_SM_W0 - A1_SM_A0) >> 4;
        const uint32_t trow = ((lane & 7) + 8 * (lane >> 4)) * 128 + (((2 * (warp & 3) + ((lane >> 3) & 1)) ^ (lane & 7)) << 4);
        uint32_t xr[10][2];
        mbar_wait(bar_f2 + 64 * wg + 64, 0);
        if (layer == 0) {
#pragma unroll
            for (int j = 0; j < 10; j += 2) ldsm_x4(&xr[j][0], sl + 51200 + (16 * (warp & 3) + (lane & 15)) * 160 + (lane >> 4) * 16 + 16 * j);
        } else {
#pragma unroll
            for (int j = 0; j < 10; j += 2) ldsm_x4_t(&xr[j][0], sl + 51200 + trow + 1024 * j);
        }
        const uint32_t ri = __shfl_sync(~0u, layer * SEQ + (wg * 2 + ((g >> 1) & 1)) * 512 + (mb * 16 + 4 * (warp & 3) + (g >> 2)) * 2 + (g & 1), lane);
        mbar_wait(bar_wo, 0);
        if (wg) mbar_wait(bar_pv, 0);
        if (wg) asm volatile("bar.sync 2, 128;" ::: "memory"); else asm volatile("bar.sync 1, 128;" ::: "memory");
        TSTAMP2(2); CSA(8);
#pragma unroll
        for (int q = 0; q < 8; q++) {
            uint32_t bo = wo_off(0) >> 4;
            if (q) {
                mbar_wait(bar_f2 + 64 * wg + 8 * q, 0);
                asm volatile("ld.shared.u32 %0, [%1];" : "=r"(bo) : "r"(que + 32 * wg + 4 * q) : "memory");
                bo = __shfl_sync(~0u, bo, 0);
                TSTAMP4(q);
                if (q % 3 == 1) CSA(9 + q / 3);
                if (q == 1 && (tid & 127) == 0) DBGC(29 + 8 * wg);
            }
            wgmma_fence();
#pragma unroll
            for (int j = 0; j < 5; j++) wgmma_n80(ac2, (j < 4 ? da0 : da1) + (q == 7 ? o7 : 0u) + (uint64_t)((q < 6 ? q * 640 : 0) + (j & 2) * 16 + (j & 1) * 2), (j < 4 ? db0 : db1) + bo + (uint64_t)((j & 2) * 160 + (j & 1) * 32), j || q);
            wgmma_commit();
            if (q == 0) {
                wgmma_wait<0>();
                if ((tid & 127) == 0) { mbar_arrive(bar_e2 + 16 * wg); mbar_arrive(bar_e2 + 8); }
            }
            if (q == 2 && wg) {
                wgmma_wait<1>();
                if (tid == 128) mbar_arrive(bar_e2 + 24);
            }
        }
        if ((tid & 127) == 0) DBGC(28 + wg * 8 + 7);
        TSTAMP2(3);
        wgmma_wait<0>();
        TSTAMP2(4); CSA(12);
        if (__any_sync(~0u, ac2[0] != ac2[0] || ac2[2] != ac2[2])) {
#pragma unroll
            for (int i = 0; i < 40; i++) ac2[i] = 0.f;
            uint32_t a[20], an[20];
            auto lda = [&](uint32_t (&r)[20], int h) {
#pragma unroll
                for (int u = 0; u < 4; u++)
                    asm volatile("ld.relaxed.gpu.global.v4.u32 {%0,%1,%2,%3}, [%4];" : "=r"(r[4 * u]), "=r"(r[4 * u + 1]), "=r"(r[4 * u + 2]), "=r"(r[4 * u + 3]) : "l"(ot + h * 20480 + o0 + u * 512) : "memory");
#pragma unroll
                for (int u = 0; u < 2; u++)
                    asm volatile("ld.relaxed.gpu.global.v2.u32 {%0,%1}, [%2];" : "=r"(r[16 + 2 * u]), "=r"(r[17 + 2 * u]) : "l"(ot + h * 20480 + o1 + u * 256) : "memory");
            };
            lda(an, 0);
#pragma unroll 5
            for (int k = lane; k < WOB / 16; k += 32)
                reinterpret_cast<uint4*>(stg + (sl - sbase))[k] = __ldcg(reinterpret_cast<const uint4*>(wo + hg * 8 * WOB) + k);
            __syncwarp();
#pragma unroll 1
            for (int h = 0; h < 8; h++) {
#pragma unroll 1
                for (int it = 0; it < SPIN_MAX; it++) {
                    uint32_t m = 0;
#pragma unroll
                    for (int k = 0; k < 20; k += 2) m = __vimax3_u32(m, an[k], an[k + 1]);
                    if (!__any_sync(~0u, m == ~0u)) break;
                    lda(an, h);
                }
#pragma unroll
                for (int k = 0; k < 20; k++) a[k] = an[k];
                lda(an, min(h + 1, 7));
                const uint32_t bp = h == hg ? sl : sbase + wo_off(h + (h < hg));
                const int r0 = 8 * ((lane & 7) >> 1) + 2 * (lane >> 3) + (lane & 1), r2 = 4 * ((lane & 7) >> 1) + 2 * ((lane >> 3) & 1) + (lane & 1);
#pragma unroll
                for (int n = 0; n < 10; n++) {
                    uint32_t b[12];
                    ldsm_x4_t(b, bp + (n >> 1) * 1024 + r0 * 32 + (((n ^ (r0 >> 2)) & 1) << 4));
                    ldsm_x4_t(b + 4, bp + 5120 + (n >> 1) * 1024 + r0 * 32 + (((n ^ (r0 >> 2)) & 1) << 4));
                    ldsm_x4_t(b + 8, bp + 10240 + (n >> 1) * 512 + r2 * 32 + (((n ^ (r2 >> 2)) & 1) << 4));
                    mma_bf16(ac2 + 4 * n, a[0], a[8], a[1], a[9], b[0], b[1]); mma_bf16(ac2 + 4 * n, a[2], a[10], a[3], a[11], b[2], b[3]);
                    mma_bf16(ac2 + 4 * n, a[4], a[12], a[5], a[13], b[4], b[5]); mma_bf16(ac2 + 4 * n, a[6], a[14], a[7], a[15], b[6], b[7]);
                    mma_bf16(ac2 + 4 * n, a[16], a[18], a[17], a[19], b[8], b[9]);
                }
            }
        }
#pragma unroll
        for (int j = 0; j < 10; j++)
#pragma unroll
            for (int hh = 0; hh < 2; hh++) {
                const uint32_t a = pack2(ac2[4 * j + 2 * hh], ac2[4 * j + 2 * hh + 1]);
                const __nv_bfloat162 r = __hadd2_rn(*reinterpret_cast<const __nv_bfloat162*>(&xr[j][hh]), *reinterpret_cast<const __nv_bfloat162*>(&a));
                xr[j][hh] = *reinterpret_cast<const uint32_t*>(&r);
            }
        const uint32_t so = sl + 30720;
#pragma unroll
        for (int j = 0; j < 10; j += 2) stsm_x4_t(so + trow + 1024 * j, xr[j][0], xr[j][1], xr[j + 1][0], xr[j + 1][1]);
        if (wg) asm volatile("bar.sync 2, 128;" ::: "memory"); else asm volatile("bar.sync 1, 128;" ::: "memory");
        TSTAMP2(5); CSA(13);
        if ((tid & 127) == 0) {
            fence_async_smem();
            asm volatile("cp.async.bulk.tensor.2d.global.shared::cta.bulk_group [%0, {%1, %2}], [%3];" ::"l"(&tmX1), "r"(mb * 128 + 64 * wg), "r"(hg * 80), "r"(so) : "memory");
            asm volatile("cp.async.bulk.commit_group;" ::: "memory");
        }
        __syncwarp();
        const float p0 = *(volatile const float*)&rw[g].x, p1 = *(volatile const float*)&rw[g + 8].x;
        float s[3][4] = {};
        const uint32_t pp[2] = {__byte_perm(__float_as_uint(p0), 0, 0x3232), __byte_perm(__float_as_uint(p1), 0, 0x3232)};
#pragma unroll
        for (int j = 0; j < 10; j += 2) {
            const uint32_t d0 = sub2(xr[j][0], pp[0]), d1 = sub2(xr[j][1], pp[1]), d2 = sub2(xr[j + 1][0], pp[0]), d3 = sub2(xr[j + 1][1], pp[1]);
            mma_bf16(s[0], xr[j][0], xr[j][1], xr[j + 1][0], xr[j + 1][1], 0x3f803f80u, 0x3f803f80u);
            mma_bf16(s[1], d0, d1, d2, d3, d0, d2);
            mma_bf16(s[2], d0, d1, d2, d3, d1, d3);
        }
        if (t == (g >> 1)) {
            float2* rp = rsum + ri;
            asm volatile("red.relaxed.gpu.global.add.v2.f32 [%0], {%1, %2};" ::"l"(rp), "f"(fmaf(-80.f, p0, s[0][0])), "f"((g & 1) ? s[1][1] : s[1][0]) : "memory");
            asm volatile("red.relaxed.gpu.global.add.v2.f32 [%0], {%1, %2};" ::"l"(rp + 4), "f"(fmaf(-80.f, p1, s[0][2])), "f"((g & 1) ? s[2][3] : s[2][2]) : "memory");
        }
        asm volatile("cp.async.bulk.wait_group.read 0;" ::: "memory");
        TSTAMP2(6); CSA(14); CSA_END;
        if (tid == 0) DBGC(63);
        if (tid == 128) DBGC(28);
        if (tid == 0) DBGCAL(2);
        GSTAMP(g_tim1, 14);
        SPAN(1 + 4 * layer, 3);
    }
}

static int h_nsm;
static void* h_sym[11];
static TileTab h_tab[2];
static CUtensorMap h_tmX0, h_tmX1, h_tmR0, h_tmR1, h_tmX1st, h_tmOut, h_tmWq, h_tmWo, h_tmWt;
typedef CUresult (*PFN_encodeTiled)(CUtensorMap*, CUtensorMapDataType, cuuint32_t, void*, const cuuint64_t*, const cuuint64_t*,
                                    const cuuint32_t*, const cuuint32_t*, CUtensorMapInterleave, CUtensorMapSwizzle,
                                    CUtensorMapL2promotion, CUtensorMapFloatOOBfill);
static void make_tmap(CUtensorMap* tm, const void* ptr, uint64_t cols, uint64_t rows, uint32_t bc, uint32_t br, CUtensorMapSwizzle sw, uint64_t pitch = 0, uint64_t hi = 0, uint32_t bh = 2) {
    static PFN_encodeTiled fn = nullptr;
    if (!fn) {
        void* p = nullptr; cudaDriverEntryPointQueryResult qr;
        cudaGetDriverEntryPoint("cuTensorMapEncodeTiled", &p, cudaEnableDefault, &qr);
        fn = (PFN_encodeTiled)p;
    }
    if (br == 0) {
        cuuint64_t dims[5] = {16, 2, rows / 8, 4, cols / 16}; cuuint64_t strides[4] = {cols * 2, cols * 16, cols * 4, 32};
        cuuint32_t box[5] = {16, 2, bc, 4, 5}; cuuint32_t es[5] = {1, 1, 1, 1, 1};
        fn(tm, CU_TENSOR_MAP_DATA_TYPE_BFLOAT16, 5, const_cast<void*>(ptr), dims, strides, box, es, CU_TENSOR_MAP_INTERLEAVE_NONE, sw,
           CU_TENSOR_MAP_L2_PROMOTION_L2_128B, CU_TENSOR_MAP_FLOAT_OOB_FILL_NONE);
        return;
    }
    if (bh == 0) {
        cuuint64_t dims[5] = {64, 64, 2, 16, 10}; cuuint64_t strides[4] = {pitch * 2, hi * 2, cols * 2, rows * 2};
        cuuint32_t box[5] = {64, 64, 2, 1, 1}; cuuint32_t es[5] = {1, 1, 1, 1, 1};
        fn(tm, CU_TENSOR_MAP_DATA_TYPE_BFLOAT16, 5, const_cast<void*>(ptr), dims, strides, box, es, CU_TENSOR_MAP_INTERLEAVE_NONE, sw,
           CU_TENSOR_MAP_L2_PROMOTION_L2_128B, CU_TENSOR_MAP_FLOAT_OOB_FILL_NONE);
        return;
    }
    if (hi) {
        cuuint64_t dims[3] = {cols, rows, hi == 64 ? 32u : hi == 16 ? 120u : 2u}; cuuint64_t strides[2] = {pitch * 2, hi * 2};
        cuuint32_t box[3] = {bc, br, bh}; cuuint32_t es[3] = {1, 1, 1};
        fn(tm, CU_TENSOR_MAP_DATA_TYPE_BFLOAT16, 3, const_cast<void*>(ptr), dims, strides, box, es, CU_TENSOR_MAP_INTERLEAVE_NONE, sw,
           CU_TENSOR_MAP_L2_PROMOTION_L2_128B, CU_TENSOR_MAP_FLOAT_OOB_FILL_NONE);
        return;
    }
    cuuint64_t dims[2] = {cols, rows}; cuuint64_t strides[1] = {(pitch ? pitch : cols) * 2};
    cuuint32_t box[2] = {bc, br}; cuuint32_t es[2] = {1, 1};
    fn(tm, CU_TENSOR_MAP_DATA_TYPE_BFLOAT16, 2, const_cast<void*>(ptr), dims, strides, box, es, CU_TENSOR_MAP_INTERLEAVE_NONE, sw,
       CU_TENSOR_MAP_L2_PROMOTION_L2_128B, CU_TENSOR_MAP_FLOAT_OOB_FILL_NONE);
}
template <typename... Args>
static void launch_pdl(void (*kern)(Args...), int grid, int block, int smem, Args... args) {
    cudaLaunchConfig_t cfg = {};
    cfg.gridDim = dim3(grid); cfg.blockDim = dim3(block); cfg.dynamicSmemBytes = smem; cfg.stream = cudaStreamPerThread;
    cudaLaunchAttribute at[1];
    at[0].id = cudaLaunchAttributeProgrammaticStreamSerialization; at[0].val.programmaticStreamSerializationAllowed = 1;
    cfg.attrs = at; cfg.numAttrs = 1;
    cudaLaunchKernelEx(&cfg, kern, args...);
}
static void launch_stage(int k, void* const* d_in, void* d_out) {
    const KgIn kg = {(const bf16*)d_in[4], (const bf16*)d_in[5], (const bf16*)d_in[6], (const bf16*)d_in[7], (const bf16*)d_in[8], (const bf16*)d_in[9], (const bf16*)d_in[0], (const bf16*)d_in[1], (const bf16*)d_in[2],
                      (uint4*)h_sym[0], (uint4*)h_sym[1], (uint4*)h_sym[2], (uint4*)h_sym[3], (uint4*)h_sym[4], (float*)h_sym[5]};
    switch (k) {
        case 0: kgen_kernel<<<128, 512, KG_SMEM, cudaStreamPerThread>>>(kg, h_tmWq, h_tmWo, h_tmWt); break;
        case 1: launch_pdl(h_nsm == 132 ? a1_kernel<true> : a1_kernel<false>, h_nsm, A1_THREADS, A1_SMEM, 0, (const bf16*)d_in[0], (const unsigned char*)h_sym[2], (float2*)h_sym[4], (uint4*)h_sym[6], h_tmX0, h_tmR0, h_tmX1st, h_tab[0]); break;
        case 3: launch_pdl(conv_kernel, DM / CV_CPB, CV_THREADS, CV_SMEM, 0, (const uint4*)h_sym[7], (const float4*)h_sym[4], (const bf16*)h_sym[8], (bf16*)h_sym[9], (const uint4*)h_sym[0], h_tmOut); break;
        case 5: launch_pdl(h_nsm == 132 ? a1_kernel<true> : a1_kernel<false>, h_nsm, A1_THREADS, A1_SMEM, 1, (const bf16*)d_in[0], (const unsigned char*)h_sym[2], (float2*)h_sym[4], (uint4*)h_sym[6], h_tmX1, h_tmR1, h_tmX1st, h_tab[1]); break;
        case 7: launch_pdl(conv_kernel, DM / CV_CPB, CV_THREADS, CV_SMEM, 1, (const uint4*)h_sym[7] + SEQ / 8, (const float4*)h_sym[4] + SEQ / 2, (const bf16*)h_sym[8], (bf16*)h_sym[10], (const uint4*)h_sym[0], h_tmOut); break;
        default: break;
    }
}
static int n_stage_kernels() { return 9; }
static const char* stage_name(int k) { const char* n[] = {"kgen", "a1", "a2", "conv", "tr", "a1", "a2", "conv", "tr"}; return n[k]; }

extern "C" void kernel_launch(void* const* d_in, const int* in_sizes, int n_in, void* d_out, int out_size) {
    (void)in_sizes; (void)n_in; (void)out_size;
    static const void *p_in = nullptr, *p_w1 = nullptr, *p_w2 = nullptr, *p_out = nullptr;
    if (p_in != d_in[0] || p_w1 != d_in[1] || p_w2 != d_in[2] || p_out != d_out) {
        cudaFuncSetAttribute(conv_kernel, cudaFuncAttributeMaxDynamicSharedMemorySize, CV_SMEM);
        cudaFuncSetAttribute(kgen_kernel, cudaFuncAttributeMaxDynamicSharedMemorySize, KG_SMEM);
        cudaFuncSetAttribute(a1_kernel<true>, cudaFuncAttributeMaxDynamicSharedMemorySize, A1_SMEM);
        cudaFuncSetAttribute(a1_kernel<false>, cudaFuncAttributeMaxDynamicSharedMemorySize, A1_SMEM);
        int dev; cudaGetDevice(&dev); cudaDeviceGetAttribute(&h_nsm, cudaDevAttrMultiProcessorCount, dev);
        if (h_nsm != 132) h_nsm = 128;
        cudaGetSymbolAddress(&h_sym[0], g_tap); cudaGetSymbolAddress(&h_sym[1], g_wq); cudaGetSymbolAddress(&h_sym[2], g_wo);
        cudaGetSymbolAddress(&h_sym[3], g_halo); cudaGetSymbolAddress(&h_sym[4], g_sum); cudaGetSymbolAddress(&h_sym[5], g_csp); cudaGetSymbolAddress(&h_sym[6], g_of);
        cudaGetSymbolAddress(&h_sym[7], g_piv); cudaGetSymbolAddress(&h_sym[8], g_x1T); cudaGetSymbolAddress(&h_sym[9], g_xcT); cudaGetSymbolAddress(&h_sym[10], g_yT);
        for (int i = 0; i < 264; i++) {
            const int s = i % 132, h = (s - 64) >> 1;
            const int t = h_nsm != 132 ? s : s < 64 ? ((s >> 1) & 7) * 16 + (s >> 4) * 2 + (s & 1) : s < 120 ? (1 + h % 7) * 16 + 8 + (h / 7) * 2 + (s & 1) : s < 124 ? 128 : s - 116;
            const int hg = (4 * (t >> 6) + (t & 3)) & 7;
            const uint64_t wp = (uint64_t)h_sym[1] + hg * 10 * WQ_STAGE;
            h_tab[i / 132].e[s] = make_uint4((uint32_t)wp, (uint32_t)(wp >> 32), ((t >> 2) & 15) | (i / 132) << 4 | hg << 8 | 5 * (hg >> 2) << 16 | (uint32_t)t << 24, 0);
        }
        for (int i = 0; i < 56; i++) {
            const uint32_t c = i < 4 || i == 30 ? 0 : i < 8 || (i > 20 && i < 26) || i == 49 ? 2 : i == 8 || i == 27 ? 3 : i == 28 ? 4 : i == 29 ? 8 : 1;
            for (int l = 0; l < 2; l++) h_tab[l].cnt[i / 7] = (i % 7 ? h_tab[l].cnt[i / 7] : 0) | c << (4 * (i % 7));
        }
        void *px1, *px2;
        cudaGetSymbolAddress(&px1, g_x1T); cudaGetSymbolAddress(&px2, g_xcT);
        make_tmap(&h_tmX0, d_in[0], 128 * 640, 64, 64, 64, CU_TENSOR_MAP_SWIZZLE_128B, 1280, 640, 0);
        make_tmap(&h_tmX1, px2, 128, 64 * XCP, 64, 64, CU_TENSOR_MAP_SWIZZLE_128B, XCP, 64, 0);
        make_tmap(&h_tmR0, d_in[0], 640, 1024, 80, 64, CU_TENSOR_MAP_SWIZZLE_NONE, 1280, 640, 1);
        make_tmap(&h_tmR1, px2, 64, 640, 64, 80, CU_TENSOR_MAP_SWIZZLE_128B, XCP, 64, 1);
        make_tmap(&h_tmX1st, px1, 2048, 640, 64, 80, CU_TENSOR_MAP_SWIZZLE_128B, XCP);
        make_tmap(&h_tmWq, d_in[1], 16, 640, 16, 32, CU_TENSOR_MAP_SWIZZLE_32B, 1920, 16, 5);
        make_tmap(&h_tmWo, d_in[2], 640, 640, 4, 0, CU_TENSOR_MAP_SWIZZLE_32B);
        make_tmap(&h_tmWt, d_in[2], 640, 640, 2, 0, CU_TENSOR_MAP_SWIZZLE_32B);
        make_tmap(&h_tmOut, d_out, 640, 1024, 80, 8, CU_TENSOR_MAP_SWIZZLE_NONE, 1280, 640, 1);
        p_in = d_in[0]; p_w1 = d_in[1]; p_w2 = d_in[2]; p_out = d_out;
    }
    for (int k = 0; k < n_stage_kernels(); k++) launch_stage(k, d_in, d_out);
}
```

```cpp
#include <cuda_runtime.h>
#include <cuda_bf16.h>
#include <stdint.h>
#include <cuda.h>

typedef __nv_bfloat16 bf16;

constexpr int SEQ = 2048;
constexpr int DM = 640;
constexpr int NMODE = 192;

__device__ __forceinline__ float bf2f(bf16 v) { return __bfloat162float(v); }
__device__ __forceinline__ float rbf(float v) {
    uint32_t r;
    asm("cvt.rn.bf16x2.f32 %0, %1, %2;" : "=r"(r) : "f"(v), "f"(0.f));
    return __uint_as_float(r);
}
__device__ __forceinline__ uint32_t pack2(float lo, float hi) {
    __nv_bfloat162 t = __floats2bfloat162_rn(lo, hi);
    return *reinterpret_cast<uint32_t*>(&t);
}
__device__ __forceinline__ void pdl_sync() {
    asm volatile("griddepcontrol.wait;" ::: "memory");
    asm volatile("griddepcontrol.launch_dependents;" ::: "memory");
}
__device__ __forceinline__ float sqrt_apx(float v) { float r; asm("sqrt.approx.ftz.f32 %0, %1;" : "=f"(r) : "f"(v)); return r; }
__device__ __forceinline__ float rcp_apx(float v) { float r; asm("rcp.approx.ftz.f32 %0, %1;" : "=f"(r) : "f"(v)); return r; }
__device__ __forceinline__ uint32_t smem_u32(const void* p) { return (uint32_t)__cvta_generic_to_shared(p); }

constexpr int TAPB = 2944, TAPE = 928;
__device__ __align__(128) uint4 g_tap[DM * TAPB / 16];
#define XPAD 64
constexpr int XCP = SEQ + XPAD;
__device__ __align__(128) bf16 g_x1T[DM * XCP];
__device__ __align__(128) bf16 g_xcT[DM * XCP];
__device__ __align__(128) uint4 g_of[128 * 1280];
constexpr int WQ_STAGE = 240 * 128, WOB = 80 * 160;
__device__ __align__(128) uint4 g_wq[8 * 10 * WQ_STAGE / 16];
__device__ __align__(128) uint4 g_wo[64 * WOB / 16];
__device__ __align__(16) float g_csp[10 * 1920];
#define FSTR 32
__device__ __align__(128) float2 g_sum[2 * SEQ + 256 * FSTR];
__device__ __align__(16) bf16 g_piv[2 * SEQ];
__device__ __align__(128) bf16 g_yT[DM * XCP];
__device__ uint32_t g_epoch;
__device__ __align__(16) unsigned long long g_rstat[SEQ];
__device__ __align__(128) uint4 g_halo[640 * 148];
__device__ __forceinline__ unsigned long long tagw(uint32_t payload, uint32_t tag) { return ((unsigned long long)tag << 32) | payload; }
__device__ __forceinline__ ulonglong2 ld_tag2(const ulonglong2* p) {
    ulonglong2 v;
    asm volatile("ld.relaxed.gpu.global.v2.u64 {%0, %1}, [%2];" : "=l"(v.x), "=l"(v.y) : "l"(p) : "memory");
    return v;
}
__device__ __forceinline__ bool tag_ok(ulonglong2 v, uint32_t tag) { return (uint32_t)(v.x >> 32) == tag && (uint32_t)(v.y >> 32) == tag; }
__device__ __forceinline__ uint32_t ld_epoch() { uint32_t v; asm volatile("ld.relaxed.gpu.global.u32 %0, [%1];" : "=r"(v) : "l"(&g_epoch) : "memory"); return v + 1; }
constexpr int SPIN_MAX = 1 << 20;
__device__ __align__(128) uint32_t g_started[128];
__device__ __forceinline__ void sm_started(int slot) { asm volatile("red.relaxed.gpu.global.add.u32 [%0], 1;" ::"l"(g_started + slot) : "memory"); }
__device__ __forceinline__ void publish(int slot) {
    asm volatile("fence.proxy.async.global;" ::: "memory");
    asm volatile("red.release.gpu.global.add.u32 [%0], 1;" ::"l"(g_started + slot) : "memory");
}
__device__ __forceinline__ void await_all(int slot, uint32_t want) {
#pragma unroll 1
    for (int it = 0; it < SPIN_MAX; it++) {
        uint32_t v;
        asm volatile("ld.acquire.gpu.global.u32 %0, [%1];" : "=r"(v) : "l"(g_started + slot) : "memory");
        if (__all_sync(~0u, (int)(v - want) >= 0)) break;
        __nanosleep(50);
    }
    asm volatile("fence.proxy.async.global;" ::: "memory");
}
__device__ __noinline__ void sm_idle(int slot) {
    if (threadIdx.x != 288) return;
    asm volatile("fence.acq_rel.gpu;" ::: "memory");
    asm volatile("fence.proxy.async.global;" ::: "memory");
    sm_started(slot);
    const uint32_t want = ld_epoch() * gridDim.x;
    pdl_sync();
#pragma unroll 1
    for (int it = 0; it < SPIN_MAX; it++) {
        uint32_t v;
        asm volatile("ld.relaxed.gpu.global.u32 %0, [%1];" : "=r"(v) : "l"(g_started + slot) : "memory");
        if ((int)(v - want) >= 0) break;
        __nanosleep(100);
    }
}
struct TileTab { uint4 e[132]; };
__device__ __forceinline__ bool elect() {
    uint32_t p;
    asm volatile("{\n.reg .pred p;\nelect.sync _|p, 0xffffffff;\nselp.b32 %0, 1, 0, p;\n}" : "=r"(p));
    return p;
}
#define DBG_SYMS
#define TSTAMP(i)
#define TSTAMP1(i)
#define TSTAMP1T(i, t)
#define TSTAMP1X(i, t)
#define SPAN(k, i)
#define GSTAMP(arr, i)
#define TSTAMP2(i)
#define TSTAMP3(i)
#define TSTAMP4(i)
#define TSTAMPK(i, t)
#define TSTAMPC(i)
#define DBGC(i)
#define DBGV(i, v)
#define DBGCAL(i)

#define CSK(i)
#define CSK_END
#define CSA(i)
#define CSA_END
#define CST(i)
#define CST_END
#define CST_EXTRA 0
__device__ __forceinline__ void mma_bf16(float* d, uint32_t a0, uint32_t a1, uint32_t a2, uint32_t a3, uint32_t b0, uint32_t b1) {
    asm volatile("mma.sync.aligned.m16n8k16.row.col.f32.bf16.bf16.f32 {%0,%1,%2,%3}, {%4,%5,%6,%7}, {%8,%9}, {%0,%1,%2,%3};"
                 : "+f"(d[0]), "+f"(d[1]), "+f"(d[2]), "+f"(d[3]) : "r"(a0), "r"(a1), "r"(a2), "r"(a3), "r"(b0), "r"(b1));
}
__device__ __forceinline__ void mma_bf16_k8(float* d, uint32_t a0, uint32_t a1, uint32_t b0) {
    asm volatile("mma.sync.aligned.m16n8k8.row.col.f32.bf16.bf16.f32 {%0,%1,%2,%3}, {%4,%5}, {%6}, {%0,%1,%2,%3};"
                 : "+f"(d[0]), "+f"(d[1]), "+f"(d[2]), "+f"(d[3]) : "r"(a0), "r"(a1), "r"(b0));
}
__device__ __forceinline__ void ldsm_x4(uint32_t* r, uint32_t addr) {
    asm volatile("ldmatrix.sync.aligned.m8n8.x4.shared.b16 {%0,%1,%2,%3}, [%4];"
                 : "=r"(r[0]), "=r"(r[1]), "=r"(r[2]), "=r"(r[3]) : "r"(addr));
}

__device__ __forceinline__ void ldsm_x4_t(uint32_t* r, uint32_t addr) {
    asm volatile("ldmatrix.sync.aligned.m8n8.x4.trans.shared.b16 {%0,%1,%2,%3}, [%4];"
                 : "=r"(r[0]), "=r"(r[1]), "=r"(r[2]), "=r"(r[3]) : "r"(addr));
}
__device__ __forceinline__ void mbar_init(uint32_t bar, int count) { asm volatile("mbarrier.init.shared::cta.b64 [%0], %1;" ::"r"(bar), "r"(count)); }
__device__ __forceinline__ void mbar_arrive(uint32_t bar) { asm volatile("mbarrier.arrive.shared::cta.b64 _, [%0];" ::"r"(bar) : "memory"); }
__device__ __forceinline__ void mbar_wait(uint32_t bar, uint32_t parity) {
    asm volatile("{\n.reg .pred p;\nWAIT_LOOP:\n"
                 "mbarrier.try_wait.parity.shared::cta.b64 p, [%0], %1;\n"
                 "@p bra.uni WAIT_DONE;\nbra.uni WAIT_LOOP;\nWAIT_DONE:\n}" ::"r"(bar), "r"(parity) : "memory");
}

__device__ __forceinline__ void mbar_expect_tx(uint32_t bar, uint32_t bytes) {
    asm volatile("mbarrier.arrive.expect_tx.shared::cta.b64 _, [%0], %1;" ::"r"(bar), "r"(bytes) : "memory");
}
__device__ __forceinline__ void tma_load_2d(uint32_t dst, const void* tmap, int c0, int c1, uint32_t bar) {
    asm volatile("cp.async.bulk.tensor.2d.shared::cluster.global.mbarrier::complete_tx::bytes [%0], [%1, {%3, %4}], [%2];"
                 ::"r"(dst), "l"(tmap), "r"(bar), "r"(c0), "r"(c1) : "memory");
}
__device__ __forceinline__ void tma_load_3d(uint32_t dst, const void* tmap, int c0, int c1, int c2, uint32_t bar) {
    asm volatile("cp.async.bulk.tensor.3d.shared::cluster.global.mbarrier::complete_tx::bytes [%0], [%1, {%3, %4, %5}], [%2];"
                 ::"r"(dst), "l"(tmap), "r"(bar), "r"(c0), "r"(c1), "r"(c2) : "memory");
}
__device__ __forceinline__ void fence_async_smem() { asm volatile("fence.proxy.async.shared::cta;" ::: "memory"); }
__device__ __forceinline__ void bulk_load(uint32_t dst, const void* src, uint32_t bytes, uint32_t bar) {
    asm volatile("cp.async.bulk.shared::cluster.global.mbarrier::complete_tx::bytes [%0], [%1], %2, [%3];"
                 ::"r"(dst), "l"(src), "r"(bytes), "r"(bar) : "memory");
}
__device__ __forceinline__ void stsm_x4(uint32_t addr, uint32_t r0, uint32_t r1, uint32_t r2, uint32_t r3) {
    asm volatile("stmatrix.sync.aligned.m8n8.x4.shared.b16 [%0], {%1,%2,%3,%4};" ::"r"(addr), "r"(r0), "r"(r1), "r"(r2), "r"(r3) : "memory");
}
__device__ __forceinline__ void stsm_x4_t(uint32_t addr, uint32_t r0, uint32_t r1, uint32_t r2, uint32_t r3) {
    asm volatile("stmatrix.sync.aligned.m8n8.x4.trans.shared.b16 [%0], {%1,%2,%3,%4};" ::"r"(addr), "r"(r0), "r"(r1), "r"(r2), "r"(r3) : "memory");
}
__device__ __forceinline__ void prefetch_tmap(const void* tmap) { asm volatile("prefetch.tensormap [%0];" ::"l"(tmap) : "memory"); }

__device__ __forceinline__ float2 cexp_at(float wr2, float wi, float p) {
    float er;
    asm("ex2.approx.ftz.f32 %0, %1;" : "=f"(er) : "f"(wr2 * p));
    float th = wi * p;
    const float k = rintf(th * 0.15915494309189535f);
    th = fmaf(k, -6.2831854820251465f, th);
    th = fmaf(k, 1.7484555314695172e-7f, th);
    return make_float2(er * __cosf(th), er * __sinf(th));
}
__device__ __forceinline__ float2 cmul(float2 a, float2 b) {
    return make_float2(fmaf(a.x, b.x, -a.y * b.y), fmaf(a.x, b.y, a.y * b.x));
}
__device__ __forceinline__ float2 csqr(float2 a) { return make_float2(fmaf(a.x, a.x, -a.y * a.y), (a.x + a.x) * a.y); }
__device__ __forceinline__ uint32_t packh(float2 v) {
    uint32_t r;
    asm("cvt.rn.f16x2.f32 %0, %1, %2;" : "=r"(r) : "f"(v.y), "f"(v.x));
    return r;
}
__device__ __forceinline__ void mma_f16(float* d, uint32_t a0, uint32_t a1, uint32_t a2, uint32_t a3, uint32_t b0, uint32_t b1) {
    asm volatile("mma.sync.aligned.m16n8k16.row.col.f32.f16.f16.f32 {%0,%1,%2,%3}, {%4,%5,%6,%7}, {%8,%9}, {%0,%1,%2,%3};"
                 : "+f"(d[0]), "+f"(d[1]), "+f"(d[2]), "+f"(d[3]) : "r"(a0), "r"(a1), "r"(a2), "r"(a3), "r"(b0), "r"(b1));
}

struct Par { const bf16 *logA, *Aim, *Cre, *Cim, *logdt, *dsk; int layer, pad; const bf16* x; uint4 *sum, *wop, *of, *halo, *tap; float* csp; uint4* wq; const bf16 *wqkv, *wo; };
struct KgMaps { CUtensorMap q, o, t; };

__device__ __forceinline__ void bulk_prefetch(const void* p, uint32_t bytes) { asm volatile("cp.async.bulk.prefetch.L2.global [%0], %1;" ::"l"(p), "r"(bytes) : "memory"); }
__device__ __forceinline__ void bulk_store(void* dst, uint32_t src, uint32_t bytes) { asm volatile("cp.async.bulk.global.shared::cta.bulk_group [%0], [%1], %2;" ::"l"(dst), "r"(src), "r"(bytes) : "memory"); }
__device__ __forceinline__ void kgen_first(const Par& in, const KgMaps& tm, const uint32_t b0, const uint32_t wbar, const bool one) {
    const uint32_t blk = blockIdx.x, sec = (blk >= 40) + (blk >= 80), it = (blk >> 3) - 5 * sec, up = (blk >> 2) & 1, hi = blk >> 6;
    auto fetch = [&](int h) {
        if (blk < 120) asm volatile("cp.async.bulk.tensor.4d.shared::cluster.global.mbarrier::complete_tx::bytes [%0], [%1, {%3, %3, %4, %5}], [%2];"
                                    ::"r"(b0 + 10240 * h), "l"(&tm.q), "r"(wbar + 8 * h), "r"(0), "r"(sec * 40 + (blk & 7) * 5), "r"(2 * it + 10 * (up ^ h)) : "memory");
    };
    auto fetch_o = [&](int i) {
        asm volatile("cp.async.bulk.tensor.5d.shared::cluster.global.mbarrier::complete_tx::bytes [%0], [%1, {%3, %3, %4, %3, %5}], [%2];"
                     ::"r"(b0 + 20480 + i * 5120), "l"(&tm.o + i), "r"(wbar + 8), "r"(0), "r"((blk & 7) * 10 + (hi + i) * 4), "r"(((blk >> 3) & 7) * 5) : "memory");
    };
    if (one) fetch(0);
    __syncwarp();
    if (blk >> 20) __trap();
    if (one) {
        bulk_prefetch(in.wqkv + blk * 9600, 19200);
        fetch(1);
        bulk_prefetch(in.wo + blk * 3200, 6400);
        fetch_o(0);
        if (hi) fetch_o(1);
        mbar_expect_tx(wbar, blk < 120 ? 10240 : 0);
        mbar_expect_tx(wbar + 8, (blk < 120 ? 15360 : 5120) + hi * 2560);
        bulk_prefetch(in.x + blk * 10240, 20480);
    }
}
template <typename F>
__device__ __forceinline__ void kgen_side(const Par& in, const uint32_t b0, const uint32_t wbar, F&& then) {
    const uint32_t blk = blockIdx.x, sec = (blk >= 40) + (blk >= 80), it = (blk >> 3) - 5 * sec, cg = (blk >> 3) & 7, hb = blk & 7;
    unsigned char* dst = reinterpret_cast<unsigned char*>(in.wq) + (hb * 10 + it) * WQ_STAGE + sec * 5120;
    unsigned char* dso = reinterpret_cast<unsigned char*>(in.wop) + (cg * 8 + (hb == cg ? 0 : hb + (hb < cg))) * WOB + (blk >> 6) * 5120;
    if (blk < 120) {
        mbar_wait(wbar, 0);
        CSK(2);
        bulk_store(dst, b0, 5120); bulk_store(dst + 15360, b0 + 5120, 5120);
    }
    if (blk < 128) {
        mbar_wait(wbar + 8, 0);
        CSK(3);
        if (blk < 120) { bulk_store(dst + 5 * WQ_STAGE, b0 + 10240, 5120); bulk_store(dst + 5 * WQ_STAGE + 15360, b0 + 15360, 5120); }
        bulk_store(dso, b0 + 20480, blk < 64 ? 5120 : 7680);
        asm volatile("cp.async.bulk.commit_group;" ::: "memory");
        asm volatile("cp.async.bulk.wait_group 0;" ::: "memory");
    }
    CSK(4);
    publish(32);
    CSK(5);
    then();
}
__device__ __forceinline__ void kgen_sums(const Par& in, const uint32_t b0, const uint32_t wbar, const int h) {
    const int lane = threadIdx.x & 31, blk = blockIdx.x;
    if (blk < 120) {
        float cs[5][4] = {};
        mbar_wait(wbar + 8 * h, 0);
#pragma unroll
        for (int a = 0; a < 4; a++)
#pragma unroll
            for (int j = 0; j < 5; j++) {
                uint32_t w[4];
                ldsm_x4_t(w, b0 + h * 10240 + j * 1024 + ((lane >> 4) * 8 + (lane & 7)) * 32 + ((((lane >> 3) ^ (lane >> 2)) & 1) << 4) + (a >> 1) * 5120 + (a & 1) * 512);
                mma_bf16(cs[j], w[0], w[1], w[2], w[3], 0x3f803f80u, 0x3f803f80u);
            }
#pragma unroll
        for (int j = 0; j < 5; j++)
            if ((lane & 3) < 2) in.csp[(blk + 120 * h) * 80 + j * 16 + (lane >> 2) + 8 * (lane & 3)] = (lane & 3) ? cs[j][2] : cs[j][0];
    }
}
struct KgPar { uint32_t pw[4], ph[4], pdt, pdsk; };
__device__ __forceinline__ void kgen_load(const Par& in, const int w11, KgPar& k) {
    const uint32_t o = blockIdx.x * 480 + min(w11 * 48, w11 * 32 + 128), ow = o + (threadIdx.x & 31), oh = o + ow + (w11 < 8 ? 64 : 0);
    k.pdt = reinterpret_cast<const unsigned short*>(in.logdt)[ow / 96];
    k.pdsk = reinterpret_cast<const unsigned short*>(in.dsk)[ow / 96];
#pragma unroll
    for (int i = 0; i < 4; i++) {
        const bf16* p = i == 0 ? in.logA : i == 1 ? in.Aim : i == 2 ? in.Cre : in.Cim;
        k.pw[i] = reinterpret_cast<const uint32_t*>(p)[ow]; k.ph[i] = reinterpret_cast<const unsigned short*>(p)[oh];
    }
}
__device__ __forceinline__ void kgen_tables(const Par& in, uint4* tabs, const int w11, const KgPar& kp) {
    const int lane = threadIdx.x & 31, grp = min(w11 >> 1, 4), warp = w11 - 2 * grp;
    const int blk = blockIdx.x, d = blk * 5 + grp, tid = warp * 32 + lane;
    uint4* tab = tabs + grp * (2 * 256);
    const uint32_t *pw = kp.pw, *ph = kp.ph;
#pragma unroll
    for (int i = 0; i < 3; i++)
        if (i < 2 || w11 * 32 + lane < 36) asm volatile("st.global.v4.u32 [%0], {%1,%1,%1,%1};" ::"l"(in.halo + blk * 740 + w11 * 32 + lane + 352 * i), "r"(~0u));
    __syncwarp();
    if (w11 == 10) {
        if (lane < 16) in.sum[blk * 16 + lane] = make_uint4(0, 0, 0, 0);
        else if (lane < 20) reinterpret_cast<uint32_t*>(in.sum + 2048)[(blk * 4 + lane - 16) * FSTR] = 0;
    } else if (w11 > 1) asm volatile("bar.arrive 9, 352;" ::: "memory");
#pragma unroll
    for (int i = 0; i < 6; i++) tabs[w11 * 256 + 32 * i + lane] = make_uint4(0, 0, 0, 0);
    __syncwarp();
    CSK(1);
    const uint32_t tw = smem_u32(tabs) + w11 * 4096;
    const int g = lane >> 2, t = lane & 3;
    const int mt = lane >> 3, r = lane & 7;
    const uint32_t st1 = tw + mt * 1024 + r * 16, st2 = tw + (mt & 1) * 1024 + (mt >> 1) * 128 + ((r ^ (mt >> 1)) << 4), st3 = tw + 2048 + mt * 128 + ((r ^ mt) << 4);
    const uint32_t lda = tw + (mt & 1) * 1024 + r * 128 + (((mt >> 1) ^ r) << 4), ldb = tw + (mt >> 1) * 1024 + r * 128 + (((mt & 1) ^ r) << 4), ldc = tw + 2048 + r * 128 + ((mt ^ r) << 4);
    auto ldsm = [](uint32_t* v, uint32_t a) {
        asm volatile("ldmatrix.sync.aligned.m8n8.x4.shared.b16 {%0,%1,%2,%3}, [%4];" : "=r"(v[0]), "=r"(v[1]), "=r"(v[2]), "=r"(v[3]) : "r"(a) : "memory");
    };
    auto mma = [](float* c, const uint32_t* a, const uint32_t* b) {
        asm("mma.sync.aligned.m16n8k16.row.col.f32.f16.f16.f32 {%0,%1,%2,%3}, {%4,%5,%6,%7}, {%8,%9}, {%0,%1,%2,%3};"
            : "+f"(c[0]), "+f"(c[1]), "+f"(c[2]), "+f"(c[3]) : "r"(a[0]), "r"(a[1]), "r"(a[2]), "r"(a[3]), "r"(b[0]), "r"(b[1]));
    };
    asm volatile("st.shared.u32 [%0], %1;" ::"r"(tw + 3072), "r"(st1 ^ st2 ^ st3 ^ lda ^ ldb ^ ldc) : "memory");
    if (in.pad) __trap();
    const float dt = rbf(expf(__uint_as_float(kp.pdt << 16)));
    const uint32_t cm = __vmaxu2(__vmaxu2(pw[2] & 0x7fff7fffu, pw[3] & 0x7fff7fffu), __byte_perm(ph[2], ph[3], 0x5410) & 0x7fff7fffu);
    const int ex = min(max((int)(__float_as_uint(__uint_as_float(__reduce_max_sync(~0u, max(cm << 16, cm & 0xffff0000u))) * dt) >> 23), 20), 240);
    const float scale = __uint_as_float((uint32_t)(127 + 10 + 127 - ex) << 23), unscale = 2.0f * __uint_as_float((uint32_t)(ex - 10) << 23);
    float k2048 = 0.f;
    float acc[5][4] = {};
    uint32_t af[4][4] = {};
    auto rest = [&] {
        uint32_t b[4][4], c[8];
#pragma unroll
        for (int k = 0; k < 4; k++) {
            ldsm(b[k], ldb ^ (k << 5));
            if (!(k & 1)) ldsm(c + 2 * k, ldc ^ (k << 5));
        }
#pragma unroll
        for (int k = 0; k < 4; k++) { mma(acc[2], af[k], b[k]); mma(acc[3], af[k], b[k] + 2); mma(acc[4], af[k], c + 2 * k); }
    };
#pragma unroll 1
    for (uint32_t sel = 0x1076; sel < (grp < 4 ? 0x6000u : 0x4000u); sel += 0x2200) {
        rest();
        auto par = [&](int i) { return __uint_as_float(__byte_perm(pw[i], ph[i], sel)); };
        const float wr2 = -rbf(expf(par(0))) * dt * 1.4426950408889634f, wi = par(1) * dt;
        const float2 y1 = cexp_at(wr2, -wi, 1.f), z8 = cexp_at(wr2, wi, 8.f), y128 = cexp_at(wr2, -wi, 128.f);
        float2 h0 = make_float2(1.f, 0.f), h1 = csqr(csqr(csqr(z8)));
        float2 g0 = make_float2(par(2) * dt * scale, -par(3) * dt * scale), g1 = cmul(g0, y128);
        const float2 y256 = csqr(y128), y512 = csqr(y256), g2b = cmul(g0, y256), y2 = csqr(y1), y4 = csqr(y2), y1024 = csqr(y512);
        float2 g2 = g2b, g3 = cmul(g0, y512), g4 = cmul(g3, y512);
        k2048 += fmaf(g4.x, y1024.x, -g4.y * y1024.y);
#pragma unroll
        for (int e = 0; e < 8; e++) {
            stsm_x4((st1 ^ (e << 4)) + e * 128, packh(h0), packh(h1), packh(g0), packh(g1));
            if (e < 7) { h0 = e ? cmul(h0, z8) : z8; h1 = cmul(h1, z8); g0 = cmul(g0, y1); g1 = cmul(g1, y1); }
        }
        __syncwarp();
        uint32_t b[4][4], v[4], u[4];
#pragma unroll
        for (int k = 0; k < 4; k++) { ldsm(af[k], lda ^ (k << 5)); ldsm(b[k], (ldb ^ (k << 5)) + 2048); }
#pragma unroll
        for (int e = 0; e < 8; e++) {
            v[2 * (e & 1)] = packh(g2); v[2 * (e & 1) + 1] = packh((e & 1) ? cmul(g3, y4) : g3); u[e & 3] = packh(g4);
            if (e & 1) stsm_x4((st2 ^ ((e - 1) << 4)) + (e - 1) * 128, v[0], v[1], v[2], v[3]);
            if ((e & 3) == 3) stsm_x4((st3 ^ ((e - 3) << 4)) + (e - 3) * 128, u[0], u[1], u[2], u[3]);
            if (e < 7) {
                g2 = e == 3 ? cmul(g2b, y128) : cmul(g2, y2);
                if (e & 1) g3 = cmul(g3, y128);
                g4 = cmul(g4, y128);
            }
            mma(acc[e & 1], af[e >> 1], b[e >> 1] + 2 * (e & 1));
        }
        __syncwarp();
        if (sel == 0x1076) CSK(3);
    }
    rest();
#pragma unroll
    for (int e = 0; e < 5; e++) k2048 += __shfl_xor_sync(~0u, k2048, 1 << e);
    {
        float* Pp = reinterpret_cast<float*>(tab + warp * 256);
        auto sw = [](int i) { return i ^ ((i >> 2) & 24); };
#pragma unroll
        for (int h = 0; h < 2; h++) {
            const int b = g + 8 * h;
            *reinterpret_cast<float2*>(Pp + sw(8 * b + 2 * t)) = make_float2(acc[0][2 * h] * unscale, acc[0][2 * h + 1] * unscale);
            *reinterpret_cast<float2*>(Pp + 128 + sw(8 * b + 2 * t)) = make_float2(acc[1][2 * h] * unscale, acc[1][2 * h + 1] * unscale);
            *reinterpret_cast<float2*>(Pp + 256 + sw(4 * b + 2 * (t & 1) + 64 * (t >> 1))) = make_float2(acc[2][2 * h] * unscale, acc[2][2 * h + 1] * unscale);
            *reinterpret_cast<float2*>(Pp + 384 + sw(2 * b + 32 * t)) = make_float2(acc[3][2 * h] * unscale, acc[3][2 * h + 1] * unscale);
            Pp[512 + sw(b + 32 * t)] = acc[4][2 * h] * unscale;
            Pp[512 + sw(b + 32 * t + 16)] = acc[4][2 * h + 1] * unscale;
        }
        if (lane == 0) Pp[640] = k2048 * unscale;
    }
    CSK(4);
    asm volatile("bar.sync %0, %1;" ::"r"(grp + 4), "r"(grp < 4 ? 64 : 96) : "memory");
    if (warp == 2) return;
    const float* Kp = reinterpret_cast<const float*>(tab);
    auto ksum = [&](int i) -> float { return rbf(Kp[i] + Kp[1024 + i] + (grp < 4 ? 0.f : Kp[2048 + i])); };
    auto ksum2 = [&](int q) -> float2 {
        q ^= (q >> 2) & 12;
        const float2 a = reinterpret_cast<const float2*>(Kp)[q], b = reinterpret_cast<const float2*>(Kp)[512 + q];
        const float2 c = grp < 4 ? make_float2(0.f, 0.f) : reinterpret_cast<const float2*>(Kp)[1024 + q];
        return make_float2(a.x + b.x + c.x, a.y + b.y + c.y);
    };
    {
        uint2* W2 = reinterpret_cast<uint2*>(in.tap + d * (TAPB / 16)) + 8;
        uint2* E4 = W2 + (TAPE - 64) / 8;
        float2 v = ksum2(64 * warp + lane), z = ksum2(64 * warp + 32 + lane), y = ksum2(128 + tid);
        const int q = (96 + tid) ^ (((96 + tid) >> 2) & 6);
        const float4 ua = reinterpret_cast<const float4*>(Kp)[q], uc = reinterpret_cast<const float4*>(Kp)[256 + q], ud = grp < 4 ? make_float4(0.f, 0.f, 0.f, 0.f) : reinterpret_cast<const float4*>(Kp)[512 + q];
        const float4 ub = make_float4(uc.x + ud.x, uc.y + ud.y, uc.z + ud.z, uc.w + ud.w);
        const float s1 = ksum(tid == 31 ? 336 : lane ? 384 : 103), s2 = ksum(tid == 31 ? 512 : tid ? 640 : 231);
        if (tid == 0) v.x += __uint_as_float(kp.pdsk << 16);
        if (tid == 63) y.y -= s1;
        const uint32_t lo = pack2(v.x, v.y), hi = pack2(z.x, z.y), tp = pack2(y.x, y.y);
        uint32_t nl = __shfl_sync(~0u, lo, lane - 1), nh = __shfl_sync(~0u, lane == 31 ? lo : hi, lane - 1), nt = __shfl_sync(~0u, tp, lane + 1);
        if (lane == 0) nl = warp ? __float_as_uint(s1) : 0u;
        if (lane == 31) nt = warp ? 0u : __float_as_uint(s1) >> 16;
        W2[64 * warp + lane] = make_uint2(__byte_perm(lo, nl, 0x7610), __byte_perm(lo, 0, 0x1032));
        W2[64 * warp + lane + 32] = make_uint2(__byte_perm(hi, nh, 0x7610), __byte_perm(hi, 0, 0x1032));
        reinterpret_cast<uint4*>(W2)[64 + tid] = make_uint4(__byte_perm(tp, __float_as_uint(s2), tid ? 0x1010 : 0x7610), __byte_perm(tp, 0, 0x1010), __byte_perm(tp, 0, 0x1032), __byte_perm(nt, tp, 0x7610));
        E4[(tid < 32 ? 159 : 209 - 32) + tid] = make_uint2(pack2(ua.x + ub.x, ua.y + ub.y), pack2(ua.z + ub.z, ua.w + ub.w - (tid == 31 ? s2 : 0.f)));
        if (tid == 63) E4[241] = make_uint2(__float_as_uint(s2) >> 16, 0u);
    }
    CSK(5);
    SPAN(0, 3);
}

#define CV_SLEEP 40
#define CV_LD "ld.relaxed.gpu.global"
#define CV_NL 1
#define CV_D2 3
#define CV_PDH 12
#define CV_PDF 4
#define CV_HAND 7
constexpr int CV_CPB = 5;
constexpr int CV_THREADS = 512;
constexpr int UPADF = 128;
constexpr int ULEN = UPADF + SEQ;
constexpr int XLEN = XCP;
constexpr int BX_5 = 0, BX_3 = 3264, BX_9 = 6528, BX_7 = 8960, BX_LEN = 11392;
constexpr int CV_SM_U = 0;
constexpr int CV_SM_T = CV_CPB * ULEN * 2;
constexpr int CV_SM_B = CV_SM_T + CV_CPB * TAPB;
constexpr int CV_SM_X = CV_SM_B + CV_CPB * BX_LEN;
constexpr int CV_SM_Y = (CV_SM_X + CV_CPB * XLEN * 2 + 127) & ~127;
constexpr int CV_SM_CNT = CV_SM_Y + CV_CPB * 8192;
constexpr int CV_SM_O = CV_SM_CNT + 128;
constexpr int CV_SMEM = CV_SM_O + 20480 + CST_EXTRA;
static_assert(ULEN % 128 == 0 && CV_SM_B % 128 == 0 && CV_SM_CNT % 128 == 0, "layout");

__device__ __forceinline__ uint32_t sub2(uint32_t x, uint32_t m) {
    const __nv_bfloat162 d = __hsub2(*reinterpret_cast<const __nv_bfloat162*>(&x), *reinterpret_cast<const __nv_bfloat162*>(&m));
    return *reinterpret_cast<const uint32_t*>(&d);
}
__device__ __forceinline__ uint32_t add2(uint32_t x, uint32_t y) {
    const __nv_bfloat162 d = __hadd2_rn(*reinterpret_cast<const __nv_bfloat162*>(&x), *reinterpret_cast<const __nv_bfloat162*>(&y));
    return *reinterpret_cast<const uint32_t*>(&d);
}
__device__ __forceinline__ void wgmma_fence() { asm volatile("wgmma.fence.sync.aligned;" ::: "memory"); }
__device__ __forceinline__ void wgmma_commit() { asm volatile("wgmma.commit_group.sync.aligned;" ::: "memory"); }
template <int N> __device__ __forceinline__ void wgmma_wait() { asm volatile("wgmma.wait_group.sync.aligned %0;" ::"n"(N) : "memory"); }
__device__ __forceinline__ uint64_t make_desc(uint32_t addr, uint32_t lbo, uint32_t sbo, uint32_t mode) {
    return (uint64_t)((addr & 0x3FFFF) >> 4) | ((uint64_t)(lbo >> 4) << 16) | ((uint64_t)(sbo >> 4) << 32) | ((uint64_t)mode << 62);
}
__device__ __forceinline__ void wgmma_rs128(float (&d)[64], uint2 hi, uint2 lo, uint64_t db, int acc) {
    asm volatile("{\n.reg .pred p;\nsetp.ne.b32 p, %69, 0;\nwgmma.mma_async.sync.aligned.m64n128k16.f32.bf16.bf16 {%0,%1,%2,%3,%4,%5,%6,%7,%8,%9,%10,%11,%12,%13,%14,%15,%16,%17,%18,%19,%20,%21,%22,%23,%24,%25,%26,%27,%28,%29,%30,%31,%32,%33,%34,%35,%36,%37,%38,%39,%40,%41,%42,%43,%44,%45,%46,%47,%48,%49,%50,%51,%52,%53,%54,%55,%56,%57,%58,%59,%60,%61,%62,%63}, {%64,%65,%66,%67}, %68, p, 1, 1, 0;\n}"
                 : "+f"(d[0]), "+f"(d[1]), "+f"(d[2]), "+f"(d[3]), "+f"(d[4]), "+f"(d[5]), "+f"(d[6]), "+f"(d[7]), "+f"(d[8]), "+f"(d[9]), "+f"(d[10]), "+f"(d[11]), "+f"(d[12]), "+f"(d[13]), "+f"(d[14]), "+f"(d[15]), "+f"(d[16]), "+f"(d[17]), "+f"(d[18]), "+f"(d[19]), "+f"(d[20]), "+f"(d[21]), "+f"(d[22]), "+f"(d[23]), "+f"(d[24]), "+f"(d[25]), "+f"(d[26]), "+f"(d[27]), "+f"(d[28]), "+f"(d[29]), "+f"(d[30]), "+f"(d[31]), "+f"(d[32]), "+f"(d[33]), "+f"(d[34]), "+f"(d[35]), "+f"(d[36]), "+f"(d[37]), "+f"(d[38]), "+f"(d[39]), "+f"(d[40]), "+f"(d[41]), "+f"(d[42]), "+f"(d[43]), "+f"(d[44]), "+f"(d[45]), "+f"(d[46]), "+f"(d[47]), "+f"(d[48]), "+f"(d[49]), "+f"(d[50]), "+f"(d[51]), "+f"(d[52]), "+f"(d[53]), "+f"(d[54]), "+f"(d[55]), "+f"(d[56]), "+f"(d[57]), "+f"(d[58]), "+f"(d[59]), "+f"(d[60]), "+f"(d[61]), "+f"(d[62]), "+f"(d[63])
                 : "r"(hi.x), "r"(hi.y), "r"(lo.x), "r"(lo.y), "l"(db), "r"(acc));
}
template <int V> struct Int { __device__ constexpr operator int() const { return V; } };
__device__ __forceinline__ void sts4(uint32_t a, const uint32_t* v) { asm volatile("st.shared.v4.u32 [%0], {%1,%2,%3,%4};" ::"r"(a), "r"(v[0]), "r"(v[1]), "r"(v[2]), "r"(v[3]) : "memory"); }
__device__ __forceinline__ uint32_t lds1(uint32_t a) { uint32_t v; asm volatile("ld.shared.u32 %0, [%1];" : "=r"(v) : "r"(a) : "memory"); return v; }
__device__ __forceinline__ uint32_t lds1v(uint32_t a) { uint32_t v; asm volatile("ld.volatile.shared.u32 %0, [%1];" : "=r"(v) : "r"(a) : "memory"); return v; }
__device__ __forceinline__ uint4 lds4(uint32_t a) { uint4 v; asm volatile("ld.shared.v4.u32 {%0,%1,%2,%3}, [%4];" : "=r"(v.x), "=r"(v.y), "=r"(v.z), "=r"(v.w) : "r"(a) : "memory"); return v; }
__device__ __forceinline__ uint4 ldx(uint32_t a) {
    uint4 v;
    asm volatile("ld.shared.v2.u32 {%0,%1}, [%4];\nld.shared.v2.u32 {%2,%3}, [%4+128];" : "=r"(v.x), "=r"(v.y), "=r"(v.z), "=r"(v.w) : "r"(a) : "memory");
    return v;
}
__device__ __forceinline__ void cv_store(unsigned char* p, uint4 x, uint4 y) {
    asm volatile("st.relaxed.gpu.global.v2.u32 [%0], {%1,%2};" ::"l"(p), "r"(add2(x.x, __byte_perm(y.x, y.y, 0x5410))), "r"(add2(x.y, __byte_perm(y.z, y.w, 0x5410))) : "memory");
    asm volatile("st.relaxed.gpu.global.v2.u32 [%0], {%1,%2};" ::"l"(p + 128), "r"(add2(x.z, __byte_perm(y.x, y.y, 0x7632))), "r"(add2(x.w, __byte_perm(y.z, y.w, 0x7632))) : "memory");
}
__device__ __forceinline__ int usw(int ch) { return ch ^ ((ch >> 3) & 1); }
__global__ void __launch_bounds__(CV_THREADS, 1) conv_kernel(int layer, const uint4* __restrict__ piv, const float4* __restrict__ sum, const bf16* __restrict__ x1T,
                                                             bf16* __restrict__ dst, const uint4* __restrict__ tap, const __grid_constant__ CUtensorMap tmOut) {
    extern __shared__ __align__(1024) unsigned char sm[];
    SPAN(3 + 4 * layer, 0);
    bf16* Us = reinterpret_cast<bf16*>(sm + CV_SM_U);
    bf16* Xs = reinterpret_cast<bf16*>(sm + CV_SM_X);
#define CV_IDX int tid; asm volatile("mov.u32 %0, %tid.x;" : "=r"(tid)); const int lane = tid & 31, warp = __shfl_sync(~0u, tid >> 5, 0);
    const int d0 = blockIdx.x * CV_CPB, tile = blockIdx.x; (void)tile;
    const uint32_t cnt = smem_u32(sm + CV_SM_CNT);
    struct Lc { uint32_t a4, a8, uc, ud, y, e4, en, sp, ss; int go; };
    auto lane_consts = [&](int lane, int c) {
        const int mat = lane >> 3, r = lane & 7, g = lane >> 2, ti = lane & 3, e = g - 2 * ti;
        const int j2 = 13 + (r ^ 1) + 8 * (mat >> 1), j3 = j2 + 2, i0 = 8 * (mat & 1);
        const uint32_t sb = smem_u32(sm), oc = sb + usw(16 * (mat >> 1) + 2 * r + (mat & 1)) * 16;
        const Lc l = {sb + CV_SM_B + c * BX_LEN + ((j2 & 1) ? BX_3 + (4 * j2 + i0 + 84) * 2 : BX_5 + (4 * j2 + i0 + 80) * 2),
                      sb + CV_SM_B + c * BX_LEN + ((j3 & 1) ? BX_7 : BX_9) + (8 * j3 + i0 + 136) * 2,
                      oc + CV_SM_U + (c * ULEN + UPADF) * 2, sb + CV_SM_U + (c * ULEN + UPADF) * 2 + usw(16 * mat + 2 * r + 2) * 16, oc + CV_SM_Y + c * 8192,
                      sb + CV_SM_T + c * TAPB + TAPE + (307 + 2 * g - ti) * 4, sb + CV_SM_T + c * TAPB + (528 + e) * 4,
                      e == -5 ? 0x4410u : e == -4 ? 0x1044u : 0x4444u, e == 3 ? 0x4410u : e == 4 ? 0x1044u : 0x4444u,
                      c * XCP * 2 + (lane >> 4) * 256 + (lane & 15) * 8};
        asm volatile("st.shared.u32 [%0], %1;" ::"r"(sb + CV_SM_CNT + 120), "r"(l.y ^ l.a4 ^ l.a8 ^ l.uc ^ l.ud ^ l.e4 ^ l.en ^ l.sp ^ l.ss ^ l.go) : "memory");
        return l;
    };
    unsigned char* const dq = reinterpret_cast<unsigned char*>(dst + (size_t)d0 * XCP);
    auto far = [&](auto T0_, const auto& seq, const Lc& lc, int c, int lane, const uint2 (&f)[20], uint32_t kk) {
        constexpr int T0 = T0_, T1 = T0 + 6, TC = T0 > 7 ? T0 : 7, NS = sizeof(seq) / sizeof(seq[0]), PD = T0 > 7 ? CV_PDH : CV_PDF;
        uint32_t bq[28], yw[4], yz[4], P, S;
        uint4 xv, yv;
        asm("prmt.b32 %0, %1, 0, %2;" : "=r"(P) : "r"(kk), "r"(lc.sp));
        asm("prmt.b32 %0, %1, 0, %2;" : "=r"(S) : "r"(kk), "r"(lc.ss));
#pragma unroll
        for (int k = 0; 2 * k < T1 - TC + 4; k++) ldsm_x4(bq + 4 * k, lc.uc + (TC - 8) * 256 + 512 * k);
#pragma unroll
        for (int k = 0; 4 * k < T1 - TC; k++) ldsm_x4(bq + 20 + 4 * k, lc.ud + (TC - 8) * 256 + 1024 * k);
        CST(3);
        mbar_wait(cnt + 8 * c, 0);
        mbar_wait(cnt + 40, 0);
        CST(4);
        float acc[6][4] = {};
        uint32_t a[PD + 1][4];
#pragma unroll
        for (int i = -PD; i < NS + 3; i++) {
            if (i + PD < NS) ldsm_x4_t(a[(i + PD) % (PD + 1)], seq[i + PD] < 32 ? lc.a4 + (seq[i + PD] - 2) * 128 : lc.a8 + (seq[i + PD] - 34) * 256);
            if (i < 0) continue;
#pragma unroll
            for (int T = T0; T < T1; T++) {
                if (i >= NS) break;
                const int ee = seq[i] < 32 ? 2 * T - 6 - seq[i] : T + 35 - seq[i];
                if (i == 0 && T >= TC) mma_bf16(acc[T - T0], P, 0u, S, P, bq[2 * (T - TC)], bq[2 * (T - TC) + 1]);
                if (i == 1 && T >= TC) mma_bf16_k8(acc[T - T0], 0u, S, bq[20 + T - TC]);
                if (i == (T >= TC ? 2 : 0)) mma_bf16(acc[T - T0], f[19].x, 0u, f[19].y, f[19].x, bq[2 * (T - TC + 4)], bq[2 * (T - TC + 4) + 1]);
                if (seq[i] < 32 ? ee >= 0 && ee <= 9 : ee >= 10) mma_bf16(acc[T - T0], a[i % (PD + 1)][0], a[i % (PD + 1)][1], a[i % (PD + 1)][2], a[i % (PD + 1)][3], f[ee].x, f[ee].y);
            }
#pragma unroll
            for (int k = 0; k < 3; k++) {
                const int o = 256 * T0 + 512 * k;
                auto at = [&](int d) { return i - d >= 0 && i - d < NS && seq[i - d < 0 ? 0 : i - d < NS ? i - d : 0] == 2 * T0 + 4 * k - 4; };
                if (at(CV_D2)) {
                    cv_store(dq + lc.go + o, xv, yv);
                    if (layer > 19 - 2 * k) __trap();
                }
                if (at(-2)) { ldsm_x4_t(yw, lc.y + o); ldsm_x4_t(yz, lc.y + 3584 + o); }
                if (at(1)) {
#pragma unroll
                    for (int q = 0; q < 4; q++) yw[q] = add2(add2(yw[q], yz[q]), pack2(acc[2 * k + (q >> 1)][2 * (q & 1)], acc[2 * k + (q >> 1)][2 * (q & 1) + 1]));
                    stsm_x4_t(lc.y + o, yw[0], yw[1], yw[2], yw[3]);
                    xv = ldx(smem_u32(Xs) + lc.go + o);
                    __syncwarp();
                    yv = lds4(smem_u32(sm + CV_SM_Y) + c * 8192 + o + usw(lane) * 16);
                    if (layer > 20 - 2 * k) __trap();
                    if (k == 2) CST(6);
                }
            }
        }
    };
    TSTAMP1X(9, 256);
    if (threadIdx.x >= 256) {
        if (threadIdx.x < 288 && elect()) {
            mbar_init(cnt + 48, 1);
            asm volatile("fence.mbarrier_init.release.cluster;" ::: "memory");
            bulk_load(smem_u32(sm + CV_SM_T), tap + d0 * (TAPB / 16), CV_CPB * TAPB, cnt + 48);
            mbar_expect_tx(cnt + 48, CV_CPB * TAPB);
        }
        CV_IDX
        const int wgu = (warp >> 2) & 1, g = lane >> 2, ti = lane & 3;
        CST(1);
        if (warp > 8 && elect()) {
            if (warp < 15) mbar_init(cnt + 8 * (warp - 9), warp == 14 ? 8 : 4);
            else if (layer) prefetch_tmap(&tmOut);
        }
        if (warp < 13 && lane < 17 - (warp == 12)) {
            const int off = warp == 12 ? CV_SM_U : CV_SM_B + (warp == 11 ? BX_7 : (warp - 8) * BX_3), str = warp == 12 ? ULEN * 2 : BX_LEN;
#pragma unroll
            for (int c = 0; c < CV_CPB; c++) *reinterpret_cast<uint4*>(sm + off + c * str + 16 * lane) = make_uint4(0, 0, 0, 0);
        }
        fence_async_smem();
        asm volatile("bar.arrive 3, 512;" ::: "memory");
        asm volatile("bar.sync 1, 256;" ::: "memory");
        TSTAMP1X(10, 256);
        asm volatile("setmaxnreg.inc.sync.aligned.u32 168;");
        const uint32_t Tc = smem_u32(sm + CV_SM_T) + (16 + 128 * (warp & 2) + 8 * (warp & 1) + g - 2 * ti) * 4;
        uint2 fa[8][2], fn[8][2];
        auto near_taps = [&](uint2 (&f)[8][2], int c) {
#pragma unroll
            for (int m = 0; m < 16; m++) f[m >> 1][m & 1] = make_uint2(lds1v(Tc + c * TAPB + 64 * (m >> 1) - 32 * (m & 1)), lds1v(Tc + c * TAPB + 64 * (m >> 1) - 32 * (m & 1) + 512));
        };
        CST(6);
        mbar_wait(cnt + 48, 0);
        TSTAMP1X(11, 256); CST(5);
        near_taps(fa, 3 * wgu);
        near_taps(fn, 2 - wgu);
        const int hc = wgu ? warp & 3 : 4;
        const Lc lc = lane_consts(lane, hc);
        TSTAMP1X(12, 256); CST(0);
        uint32_t ya = smem_u32(sm + CV_SM_Y) + wgu * 8192 + (warp & 2) * 2048 + usw(2 * lane + (warp & 1)) * 16;
        uint64_t db = make_desc(smem_u32(Us + wgu * ULEN + UPADF), 16, 256, 3);
        if (wgu) { asm volatile("bar.sync 6, 384;" ::: "memory"); fence_async_smem(); }
        int c = wgu;
        auto chain = [&](const uint2 (&f)[8][2], auto&& meanwhile) {
            float acc[64];
            asm volatile("bar.sync %0, %1;" ::"r"(c ? 4 + wgu : 2), "r"(c ? 256 : 384) : "memory");
            TSTAMPC(1 + 3 * c);
            if (c < 2) CST(7);
            if (c == 0) fence_async_smem();
            wgmma_fence();
#pragma unroll
            for (int m = 0; m < 8; m++) {
                wgmma_rs128(acc, f[m][0], f[m][1], db - (uint64_t)(2 * m), m);
                if (m == CV_HAND && c < 4) asm volatile("bar.arrive %0, 256;" ::"r"(5 - wgu) : "memory");
            }
            wgmma_commit();
            asm volatile("griddepcontrol.launch_dependents;" ::: "memory");
            TSTAMPC(2 + 3 * c); CST(13 + (c >> 1));
            meanwhile();
            wgmma_wait<0>();
            TSTAMPC(3 + 3 * c); CST(10 + (c >> 1));
            uint32_t w[16];
#pragma unroll
            for (int j = 0; j < 16; j++) w[j] = j ? pack2(acc[4 * j] + acc[4 * j - 2], acc[4 * j + 1] + acc[4 * j - 1]) : pack2(acc[0], acc[1]);
#pragma unroll
            for (int j = 0; j < 16; j += 4) stsm_x4_t(ya + 256 * j, w[j], w[j + 1], w[j + 2], w[j + 3]);
            __syncwarp();
            if (lane == 0) mbar_arrive(cnt + 8 * c);
            c += 2; ya += 16384; db += ULEN / 4;
        };
        const uint32_t e4 = lc.e4, e8 = e4 + 428 - 4 * g;
        uint2 fl[4];
        uint32_t kk;
#pragma unroll 1
        for (;;) {
            if (c != 1) chain(fa, [&] {
                if (c == 3 || warp + c == 12) {
#pragma unroll
                    for (int k = 0; k < 19; k++) (k < 16 ? fn[(k >> 1) & 7][k & 1] : fl[k & 3]) = make_uint2(lds1(k < 10 ? e4 + 32 * k + 16 : e8 + 32 * k - 304), lds1(k < 10 ? e4 + 32 * k : e8 + 32 * k - 320));
                    fl[3] = make_uint2(lds1(lc.en), lds1(lc.en - 32));
                    kk = lds1(smem_u32(sm + CV_SM_T) + TAPB * hc + TAPE + 1672);
                }
            });
            if (c > 4) break;
            if (c == 2) { asm volatile("bar.sync 7, 384;" ::: "memory"); fence_async_smem(); }
            chain(fn, [&] { if (c == 2) near_taps(fa, 4); });
        }
        TSTAMP1X(6, 256); CST(2);
        if (wgu || warp == 8) {
            constexpr int seq[29] = {5, 6, 32, 7, 33, 8, 34, 9, 35, 10, 36, 11, 12, 13, 14, 15, 16, 17, 37, 18, 38, 19, 20, 21, 39, 22, 40, 23, 24};
            uint2 f[20];
#pragma unroll
            for (int k = 0; k < 20; k++) f[k] = k < 16 ? fn[(k >> 1) & 7][k & 1] : fl[k & 3];
            far(Int<10>(), seq, lc, hc, lane, f, kk);
        }
    } else {
        asm volatile("setmaxnreg.dec.sync.aligned.u32 88;");
        CV_IDX
        CST(5);
        const uint4* ppv = piv + tid;
        const float4* psv = sum + tid;
        const uint2* pxv = reinterpret_cast<const uint2*>(x1T + (size_t)d0 * XCP) + (tid >> 4) * 32 + (tid & 15);
        asm volatile("st.shared.u64 [%0], %1;" ::"r"(smem_u32(sm + CV_SM_O) + tid * 16), "l"((uint64_t)ppv ^ (uint64_t)psv ^ (uint64_t)pxv) : "memory");
        const int tc = (0x04302100 >> (4 * warp)) & 7;
        const Lc lc = lane_consts(lane, tc);
        pdl_sync();
        SPAN(3 + 4 * layer, 1);
        TSTAMP(0); CST(0);
        if (tid == 0) TSTAMPC(0);
        if (threadIdx.x == 0) { GSTAMP(g_tim, 15); }
        float4 sv[4];
        uint4 pv;
#pragma unroll
        for (int k = 0; k < 4; k++)
            asm volatile(CV_LD ".v4.f32 {%0,%1,%2,%3}, [%4];" : "=f"(sv[k].x), "=f"(sv[k].y), "=f"(sv[k].z), "=f"(sv[k].w) : "l"(psv + 256 * k) : "memory");
        asm volatile(CV_LD ".v4.u32 {%0,%1,%2,%3}, [%4];" : "=r"(pv.x), "=r"(pv.y), "=r"(pv.z), "=r"(pv.w) : "l"(ppv) : "memory");
        uint2 xe[CV_CPB], xo[CV_CPB];
#pragma unroll
        for (int c = 0; c < CV_NL; c++) {
            asm volatile(CV_LD ".v2.u32 {%0,%1}, [%2];" : "=r"(xe[c].x), "=r"(xe[c].y) : "l"(pxv + c * (XCP / 4)) : "memory");
            asm volatile(CV_LD ".v2.u32 {%0,%1}, [%2];" : "=r"(xo[c].x), "=r"(xo[c].y) : "l"(pxv + c * (XCP / 4) + 16) : "memory");
        }
#define CV_XD 300
#define CV_XW 0
        if (warp == CV_XW) {
            if (elect()) {
                const uint32_t c0 = clock();
                mbar_init(cnt + 56, 1);
                asm volatile("fence.mbarrier_init.release.cluster;" ::: "memory");
                mbar_expect_tx(cnt + 56, CV_CPB * 4096);
                while (clock() - c0 < CV_XD) ;
#pragma unroll
                for (int c = CV_NL; c < CV_CPB + CV_NL; c++) bulk_load(smem_u32(Xs + (c % CV_CPB) * XLEN), x1T + (size_t)(d0 + c % CV_CPB) * XCP, 4096, cnt + 56);
            }
            __syncwarp();
            CST(15);
        }
        constexpr float idm = 1.0f / DM;
        uint32_t mw[4];
        float rs[8];
#pragma unroll
        for (int k = 0; k < 4; k++) {
            const uint32_t pw = k == 0 ? pv.x : k == 1 ? pv.y : k == 2 ? pv.z : pv.w;
            mw[k] = pack2(fmaf(sv[k].x, idm, __uint_as_float(pw << 16)), fmaf(sv[k].z, idm, __uint_as_float(pw & 0xffff0000u)));
            uint32_t vr;
            asm("cvt.rn.relu.bf16x2.f32 %0, %1, %2;" : "=r"(vr) : "f"(fmaf(sv[k].z * -idm, sv[k].z, sv[k].w) * idm), "f"(fmaf(sv[k].x * -idm, sv[k].x, sv[k].y) * idm));
            const uint32_t ve = pack2(__uint_as_float(vr << 16) + 1e-5f, __uint_as_float(vr & 0xffff0000u) + 1e-5f);
            const uint32_t sd = pack2(sqrt_apx(__uint_as_float(ve << 16)), sqrt_apx(__uint_as_float(ve & 0xffff0000u)));
            rs[2 * k] = rcp_apx(__uint_as_float(sd << 16)); rs[2 * k + 1] = rcp_apx(__uint_as_float(sd & 0xffff0000u));
        }
        if (rs[0] != 123.f) TSTAMP(13);
        const uint32_t ua = smem_u32(Us) + usw(tid + UPADF / 8) * 16;
        uint32_t uw[CV_CPB][4];
#pragma unroll
        for (int c = 0; c < CV_CPB; c++) {
            if (c == CV_NL) {
                if (warp == CV_XW) { mbar_wait(cnt + 56, 0); CST(7); }
                asm volatile("bar.sync 10, 256;" ::: "memory");
            }
            if (c == 1 || c == 2) {
#pragma unroll
                for (int k = c; k < (c == 1 ? 2 : CV_CPB); k++) {
 const uint4 v = ldx(smem_u32(Xs + k * XLEN) + (tid >> 4) * 256 + (tid & 15) * 8); xe[k] = make_uint2(v.x, v.y); xo[k] = make_uint2(v.z, v.w); }
            }
            const uint32_t e0 = sub2(xe[c].x, mw[0]), e1 = sub2(xe[c].y, mw[1]), o0 = sub2(xo[c].x, mw[2]), o1 = sub2(xo[c].y, mw[3]);
            uw[c][0] = pack2(__uint_as_float(e0 << 16) * rs[0], __uint_as_float(o0 << 16) * rs[4]); uw[c][1] = pack2(__uint_as_float(e0 & 0xffff0000u) * rs[1], __uint_as_float(o0 & 0xffff0000u) * rs[5]);
            uw[c][2] = pack2(__uint_as_float(e1 << 16) * rs[2], __uint_as_float(o1 << 16) * rs[6]); uw[c][3] = pack2(__uint_as_float(e1 & 0xffff0000u) * rs[3], __uint_as_float(o1 & 0xffff0000u) * rs[7]);
            asm volatile("st.shared.v4.u32 [%0], {%1,%2,%3,%4};" ::"r"(ua + c * ULEN * 2), "r"(uw[c][0]), "r"(uw[c][1]), "r"(uw[c][2]), "r"(uw[c][3]) : "memory");
            if (c < 2) {
                asm volatile("bar.arrive %0, 384;" ::"r"(2 + 4 * c) : "memory");
                if (layer > 29 - c) __trap();
                CST(11 + c);
            }
        }
        asm volatile("bar.arrive 7, 384;" ::: "memory");
        asm volatile("bar.sync 3, 512;" ::: "memory");
        TSTAMP(1); CST(1);
        {
            auto box = [&](auto c0, auto c1, int chunk, int cb, bool full) {
                const uint32_t ea = smem_u32(Us + cb * ULEN) + usw(chunk + UPADF / 8 + (lane ? 1 : -1)) * 16, bx = smem_u32(sm + CV_SM_B + cb * BX_LEN) + chunk * 16;
                uint32_t lo[CV_CPB][4], hi[CV_CPB][2];
#pragma unroll
                for (int c = c0; c < c1; c++) {
                    lo[c][0] = 0;
#pragma unroll
                    for (int k = 1; k < 4; k++) lo[c][k] = __shfl_up_sync(~0u, uw[c][k], 1);
#pragma unroll
                    for (int k = 0; k < 2; k++) hi[c][k] = __shfl_down_sync(~0u, uw[c][k], 1);
                }
#pragma unroll
                for (int c = c0; c < c1; c++)
                    asm volatile("{\n.reg .pred p, q;\nsetp.eq.s32 p, %7, 0;\nsetp.eq.s32 q, %7, 31;\n@p ld.shared.v4.u32 {%0,%1,%2,%3}, [%6];\n@q ld.shared.v2.u32 {%4,%5}, [%6];\n}"
                                 : "+r"(lo[c][0]), "+r"(lo[c][1]), "+r"(lo[c][2]), "+r"(lo[c][3]), "+r"(hi[c][0]), "+r"(hi[c][1]) : "r"(ea + c * ULEN * 2), "r"(lane) : "memory");
#pragma unroll
                for (int c = c0; c < c1; c++) {
                    const uint32_t e[9] = {lo[c][1], lo[c][2], lo[c][3], uw[c][0], uw[c][1], uw[c][2], uw[c][3], hi[c][0], hi[c][1]};
                    uint32_t o[8], p[8], t[7], b3[5], b5[7];
#pragma unroll
                    for (int i = 0; i < 8; i++) { o[i] = __byte_perm(e[i], e[i + 1], 0x5432); p[i] = add2(e[i], o[i]); }
#pragma unroll
                    for (int i = 0; i < 5; i++) b3[i] = add2(o[i], p[i + 1]);
                    sts4(bx + c * BX_LEN + BX_3 + 160, b3);
#pragma unroll
                    for (int i = 1; i < 7; i++) { t[i] = add2(p[i], p[i + 1]); b5[i] = add2(t[i], e[i + 2]); }
                    sts4(bx + c * BX_LEN + BX_5 + 160, b5 + 2);
                    if (full) {
#pragma unroll
                        for (int i = 1; i < 5; i++) { b3[i] = add2(b3[i], t[i + 2]); t[i] = add2(t[i], b5[i + 2]); }
                        sts4(bx + c * BX_LEN + BX_7 + 272, b3 + 1);
                        sts4(bx + c * BX_LEN + BX_9 + 272, t + 1);
                    }
                }
            };
            auto reload = [&](int c, uint32_t a) { const uint4 v = lds4(a); uw[c][0] = v.x; uw[c][1] = v.y; uw[c][2] = v.z; uw[c][3] = v.w; };
            if (warp >= 6) {
#pragma unroll
                for (int c = 0; c < 3; c++) reload(c, ua - 1024 + (c + 2) * ULEN * 2);
            }
            if (warp >= 4) {
#pragma unroll
                for (int c = 3; c < 5; c++) reload(c, ua - 2048 + c * ULEN * 2);
            }
            box(Int<0>(), Int<3>(), warp < 6 ? tid : tid - 64, warp < 6 ? 0 : 2, warp < 4);
            if (warp >= 4) box(Int<3>(), Int<5>(), tid - 128, 0, true);
            else if (tid >= 128 - CV_CPB) {
                const int c = 127 - tid;
                const uint2 v = *reinterpret_cast<const uint2*>(Us + c * ULEN + UPADF);
                const float s1 = __uint_as_float(v.x << 16), s2 = s1 + __uint_as_float(v.x & 0xffff0000u), s3 = s2 + __uint_as_float(v.y << 16), s4 = s3 + __uint_as_float(v.y & 0xffff0000u);
                unsigned char* bc = sm + CV_SM_B + c * BX_LEN;
                *reinterpret_cast<uint32_t*>(bc + BX_5 + 156) = pack2(s1, s2);
                *reinterpret_cast<uint2*>(bc + BX_7 + 264) = make_uint2(v.x << 16, pack2(s2, s3));
                *reinterpret_cast<uint2*>(bc + BX_9 + 264) = make_uint2(pack2(s1, s2), pack2(s3, s4));
            }
        }
        __syncwarp();
        if (lane == 0) mbar_arrive(cnt + 40);
        TSTAMP(2); CST(2);
        if (layer && blockIdx.x == 0 && tid == 224) g_epoch = ld_epoch();
        __syncwarp();
        if ((0x6e >> warp) & 1) {
            constexpr int seq[16] = {0, 1, 2, 3, 4, 5, 6, 32, 7, 8, 9, 33, 10, 34, 11, 12};
            uint2 f[20];
            mbar_wait(cnt, 0);
            const uint32_t e8 = lc.e4 + 428 - (lane & 28);
#pragma unroll
            for (int k = 0; k < 13; k++) f[k] = make_uint2(lds1(k < 10 ? lc.e4 + 32 * k + 16 : e8 + 32 * k - 304), lds1(k < 10 ? lc.e4 + 32 * k : e8 + 32 * k - 320));
            f[19] = make_uint2(lds1(lc.en), lds1(lc.en - 32));
            far(Int<4>(), seq, lc, tc, lane, f, lds1(smem_u32(sm + CV_SM_T) + TAPB * tc + TAPE + 1672));
        }
    }
    {
        CV_IDX
        if ((0xc91 >> warp) & 1) {
            const int c = __popc(0xc91 & ((1 << warp) - 1));
            uint4 xv[2], yv[2];
#pragma unroll
            for (int k = 0; k < 2; k++) xv[k] = ldx(smem_u32(Xs + c * XLEN) + 512 * k + (lane >> 4) * 256 + (lane & 15) * 8);
            const uint32_t u0 = lds1(smem_u32(Us + c * ULEN) + (lane == 31 ? UPADF * 2 : 0));
            mbar_wait(cnt + 8 * c, 0);
#pragma unroll
            for (int k = 0; k < 2; k++) yv[k] = lds4(smem_u32(sm + CV_SM_Y) + c * 8192 + 512 * k + usw(lane) * 16);
            const uint4 yz = lds4(smem_u32(sm + CV_SM_Y) + c * 8192 + 4096 + usw(lane) * 16);
            const float kk = __uint_as_float(lds1(smem_u32(sm + CV_SM_T) + TAPB * c + TAPE + 1272) << 16);
            yv[1].x = add2(yv[1].x, yz.x); yv[1].y = add2(yv[1].y, yz.y); yv[1].z = add2(yv[1].z, yz.z);
            yv[1].w = pack2(fmaf(kk, __uint_as_float(u0 << 16), __uint_as_float(yv[1].w << 16) + __uint_as_float(yz.w << 16)),
                            fmaf(kk, __uint_as_float(u0 << 16) + __uint_as_float(u0 & 0xffff0000u), __uint_as_float(yv[1].w & 0xffff0000u) + __uint_as_float(yz.w & 0xffff0000u)));
#pragma unroll
            for (int k = 0; k < 2; k++) cv_store(dq + c * XCP * 2 + (lane >> 4) * 256 + (lane & 15) * 8 + 512 * k, xv[k], yv[k]);
        }
        TSTAMP(4); CST(8);
        if (layer == 1) {
            const int rb = (blockIdx.x >> 3) + (warp & 8) * 2, cg = blockIdx.x & 7, ch = (tid >> 3) & 31;
            const bf16* src = dst + (size_t)(cg * 80 + ch) * XCP + rb * 64 + (tid & 7) * 8;
            uint32_t v[3][4];
            __syncthreads();
            if (warp & 8) { const uint32_t c0 = clock(); while (clock() - c0 < 300) ; }
            uint32_t todo = (warp & 4) ? 3 : 7;
#pragma unroll 1
            for (int it = 0; it < SPIN_MAX; it++) {
#pragma unroll
                for (int k = 0; k < 3; k++)
                    if (todo >> k & 1)
                        asm volatile("ld.relaxed.gpu.global.v4.u32 {%0,%1,%2,%3}, [%4];" : "=r"(v[k][0]), "=r"(v[k][1]), "=r"(v[k][2]), "=r"(v[k][3]) : "l"(src + k * (32 * XCP)) : "memory");
#pragma unroll
                for (int k = 0; k < 3; k++)
                    if ((todo >> k & 1) && v[k][0] != ~0u && v[k][1] != ~0u && v[k][2] != ~0u && v[k][3] != ~0u) {
                        *reinterpret_cast<uint4*>(sm + (32 * k + ch) * 272 + ((tid & 7) + (warp & 8)) * 16) = make_uint4(v[k][0], v[k][1], v[k][2], v[k][3]);
                        todo ^= 1u << k;
                    }
                if (!todo) break;
                __nanosleep(CV_SLEEP);
            }
            __syncwarp();
            asm volatile("bar.sync %0, 256;" ::"r"(8 + (warp >> 3)) : "memory");
            uint32_t w[12];
#pragma unroll
            for (int k = 0; k < 3; k++) ldsm_x4(&w[4 * k], smem_u32(sm) + min(32 * k + lane, 79) * 272 + warp * 16);
            const uint32_t ot = smem_u32(sm + CV_SM_O) + warp * 1280, oa = ot + (lane & 7) * 160 + (lane >> 3) * 16;
            stsm_x4_t(oa, w[0], w[1], w[2], w[3]);
            stsm_x4_t(oa + 64, w[4], w[5], w[6], w[7]);
            asm volatile("stmatrix.sync.aligned.m8n8.x2.trans.shared.b16 [%0], {%1,%2};" ::"r"(oa + 128), "r"(w[8]), "r"(w[9]) : "memory");
            fence_async_smem();
            __syncwarp();
            if (lane == 0) {
                asm volatile("cp.async.bulk.tensor.3d.global.shared::cta.bulk_group [%0, {%1, %2, %3}], [%4];" ::"l"(&tmOut), "r"(cg * 80), "r"((rb >> 1) * 64 + 8 * (warp & 7)), "r"(rb & 1), "r"(ot) : "memory");
                asm volatile("cp.async.bulk.commit_group;" ::: "memory");
                asm volatile("cp.async.bulk.wait_group.read 0;" ::: "memory");
            }
        }
    }
    TSTAMP(3); CST(9); CST_END;
    GSTAMP(g_tim, 14);
    SPAN(3 + 4 * layer, 3);
}

template <int TA, int TB>
__device__ __forceinline__ void wgmma_n240(float (&d)[120], uint64_t da, uint64_t db, int acc) {
    asm volatile("{\n.reg .pred p;\nsetp.ne.b32 p, %124, 0;\nwgmma.mma_async.sync.aligned.m64n240k16.f32.bf16.bf16 {%0,%1,%2,%3,%4,%5,%6,%7,%8,%9,%10,%11,%12,%13,%14,%15,%16,%17,%18,%19,%20,%21,%22,%23,%24,%25,%26,%27,%28,%29,%30,%31,%32,%33,%34,%35,%36,%37,%38,%39,%40,%41,%42,%43,%44,%45,%46,%47,%48,%49,%50,%51,%52,%53,%54,%55,%56,%57,%58,%59,%60,%61,%62,%63,%64,%65,%66,%67,%68,%69,%70,%71,%72,%73,%74,%75,%76,%77,%78,%79,%80,%81,%82,%83,%84,%85,%86,%87,%88,%89,%90,%91,%92,%93,%94,%95,%96,%97,%98,%99,%100,%101,%102,%103,%104,%105,%106,%107,%108,%109,%110,%111,%112,%113,%114,%115,%116,%117,%118,%119}, %120, %121, p, 1, 1, %122, %123;\n}"
                 : "+f"(d[0]), "+f"(d[1]), "+f"(d[2]), "+f"(d[3]), "+f"(d[4]), "+f"(d[5]), "+f"(d[6]), "+f"(d[7]), "+f"(d[8]), "+f"(d[9]), "+f"(d[10]), "+f"(d[11]), "+f"(d[12]), "+f"(d[13]), "+f"(d[14]), "+f"(d[15]), "+f"(d[16]), "+f"(d[17]), "+f"(d[18]), "+f"(d[19]), "+f"(d[20]), "+f"(d[21]), "+f"(d[22]), "+f"(d[23]), "+f"(d[24]), "+f"(d[25]), "+f"(d[26]), "+f"(d[27]), "+f"(d[28]), "+f"(d[29]), "+f"(d[30]), "+f"(d[31]), "+f"(d[32]), "+f"(d[33]), "+f"(d[34]), "+f"(d[35]), "+f"(d[36]), "+f"(d[37]), "+f"(d[38]), "+f"(d[39]), "+f"(d[40]), "+f"(d[41]), "+f"(d[42]), "+f"(d[43]), "+f"(d[44]), "+f"(d[45]), "+f"(d[46]), "+f"(d[47]), "+f"(d[48]), "+f"(d[49]), "+f"(d[50]), "+f"(d[51]), "+f"(d[52]), "+f"(d[53]), "+f"(d[54]), "+f"(d[55]), "+f"(d[56]), "+f"(d[57]), "+f"(d[58]), "+f"(d[59]), "+f"(d[60]), "+f"(d[61]), "+f"(d[62]), "+f"(d[63]), "+f"(d[64]), "+f"(d[65]), "+f"(d[66]), "+f"(d[67]), "+f"(d[68]), "+f"(d[69]), "+f"(d[70]), "+f"(d[71]), "+f"(d[72]), "+f"(d[73]), "+f"(d[74]), "+f"(d[75]), "+f"(d[76]), "+f"(d[77]), "+f"(d[78]), "+f"(d[79]), "+f"(d[80]), "+f"(d[81]), "+f"(d[82]), "+f"(d[83]), "+f"(d[84]), "+f"(d[85]), "+f"(d[86]), "+f"(d[87]), "+f"(d[88]), "+f"(d[89]), "+f"(d[90]), "+f"(d[91]), "+f"(d[92]), "+f"(d[93]), "+f"(d[94]), "+f"(d[95]), "+f"(d[96]), "+f"(d[97]), "+f"(d[98]), "+f"(d[99]), "+f"(d[100]), "+f"(d[101]), "+f"(d[102]), "+f"(d[103]), "+f"(d[104]), "+f"(d[105]), "+f"(d[106]), "+f"(d[107]), "+f"(d[108]), "+f"(d[109]), "+f"(d[110]), "+f"(d[111]), "+f"(d[112]), "+f"(d[113]), "+f"(d[114]), "+f"(d[115]), "+f"(d[116]), "+f"(d[117]), "+f"(d[118]), "+f"(d[119])
                 : "l"(da), "l"(db), "n"(TA), "n"(TB), "r"(acc));
}

__device__ __forceinline__ void wgmma_n80(float (&d)[40], uint64_t da, uint64_t db, int acc) {
    asm volatile("{\n.reg .pred p;\nsetp.ne.b32 p, %42, 0;\nwgmma.mma_async.sync.aligned.m64n80k16.f32.bf16.bf16 {%0,%1,%2,%3,%4,%5,%6,%7,%8,%9,%10,%11,%12,%13,%14,%15,%16,%17,%18,%19,%20,%21,%22,%23,%24,%25,%26,%27,%28,%29,%30,%31,%32,%33,%34,%35,%36,%37,%38,%39}, %40, %41, p, 1, 1, 0, 1;\n}"
                 : "+f"(d[0]), "+f"(d[1]), "+f"(d[2]), "+f"(d[3]), "+f"(d[4]), "+f"(d[5]), "+f"(d[6]), "+f"(d[7]), "+f"(d[8]), "+f"(d[9]), "+f"(d[10]), "+f"(d[11]), "+f"(d[12]), "+f"(d[13]), "+f"(d[14]), "+f"(d[15]), "+f"(d[16]), "+f"(d[17]), "+f"(d[18]), "+f"(d[19]), "+f"(d[20]), "+f"(d[21]), "+f"(d[22]), "+f"(d[23]), "+f"(d[24]), "+f"(d[25]), "+f"(d[26]), "+f"(d[27]), "+f"(d[28]), "+f"(d[29]), "+f"(d[30]), "+f"(d[31]), "+f"(d[32]), "+f"(d[33]), "+f"(d[34]), "+f"(d[35]), "+f"(d[36]), "+f"(d[37]), "+f"(d[38]), "+f"(d[39])
                 : "l"(da), "l"(db), "r"(acc));
}

constexpr int A1_THREADS = 384;
constexpr int A1_NST = 4;
#define A1_SKEW 8
constexpr int A1_STAGE = 16384 + WQ_STAGE;
constexpr int A1_KVP = 336;
constexpr int A1_SM_KV = 2 * A1_STAGE;
constexpr int A1_SM_END = A1_NST * A1_STAGE;
constexpr int A1_SM_BAR = A1_SM_END + 3072 + 3 * WOB + 64;
constexpr int A1_SM_RS = A1_SM_END + 512;
constexpr int A1_SM_W0 = A1_SM_END + 3072, A1_SM_W3 = A1_SM_END - 3 * WOB, A1_SM_A1 = 2 * WOB, A1_SM_A0 = A1_SM_A1 + 61440;
constexpr int A1_SM_XA = A1_SM_W0 + 2 * WOB, A1_SM_XB = A1_SM_XA + 2048;
constexpr int A1_SMEM = A1_SM_BAR + 512 + 7 * CST_EXTRA / 4;
static_assert(A1_SM_W3 >= A1_SM_KV + 144 * A1_KVP && A1_SM_W3 % 512 == 0 && A1_SM_A1 % 1024 == 0 && A1_SM_A0 <= A1_SM_KV && A1_SM_A0 + 61440 <= A1_SM_W3 && A1_SMEM <= 232448 && 11 * 4096 <= A1_STAGE, "layout");
__device__ __forceinline__ constexpr uint32_t wo_off(int h) { return h * WOB + (h < 3 ? A1_SM_W0 : h < 6 ? A1_SM_W3 - 3 * WOB : -6 * WOB); }
#define A1_FRED "red.relaxed.gpu.global.add.u32"
#define A1_FLD "ld.acquire.gpu.global.u32"
#define ST_SLEEP 20
#define ST_SLEEP0 300
#define WO_LATE bar_done
#define A1_P0 2
#define A1_PW (kb - 2)
#define A1_FSPIN SPIN_MAX
#define A1_FSLEEP 40
#define YT_LAYER 1
#define WOT 352
#define A1_WOAT 6

template <int L>
__device__ __forceinline__ void a1_mainloop(float (&acc)[120], uint32_t sbase, uint32_t bars, int wg, int tile) {
    constexpr int layer = L; (void)layer;
    const uint64_t da0 = L ? make_desc(sbase + wg * 8192, 8192, 1024, 1) : make_desc(sbase + wg * 8192, 16, 1024, 1), db0 = make_desc(sbase + 16384, 1024, 256, 3);
#pragma unroll 1
    for (int t = 0;; t++) {
        const int st = t % A1_NST;
        mbar_wait(bars + 8 * st, (t / A1_NST) & 1);
        if (t == A1_SKEW && wg == 0) mbar_wait(bars + 160, 0);
        TSTAMP3(1 + t);
        if (t == 0) CSA(0);
        CSK(6 + t);
        wgmma_fence();
#pragma unroll
        for (int kk = 0; kk < 4; kk++) wgmma_n240<L, 1>(acc, da0 + (uint32_t)(st * (A1_STAGE / 16) + kk * (L ? 128 : 2)), db0 + (uint32_t)(st * (A1_STAGE / 16) + (kk >> 1) * (WQ_STAGE / 32) + (kk & 1) * 32), kk ? 1 : t);
        wgmma_commit();
        if (t == 9) break;
        if (t == A1_SKEW - 1 && wg == 0) wgmma_wait<0>(); else wgmma_wait<1>();
        if (t > 0 && (threadIdx.x & 127) == 0) {
            if (t != A1_SKEW || wg) mbar_arrive(bars + 8 * (A1_NST + (t - 1) % A1_NST));
            if (t == A1_SKEW - 1 && wg == 0) mbar_arrive(bars + 8 * (A1_NST + t % A1_NST));
        }
    }
}

template <bool MAP>
__global__ void __launch_bounds__(A1_THREADS, 1) a1_kernel(const __grid_constant__ Par in, const __grid_constant__ CUtensorMap tmX, const __grid_constant__ CUtensorMap tmR,
                                                           const __grid_constant__ CUtensorMap tmX1, const __grid_constant__ KgMaps tmW, const __grid_constant__ TileTab tab) {
#define layer in.layer
    const unsigned char* const wo = reinterpret_cast<const unsigned char*>(in.wop);
    float2* const rsum = reinterpret_cast<float2*>(in.sum);
    uint4* const of = in.of;
    extern __shared__ __align__(1024) unsigned char stg[];
    const uint32_t sbase = smem_u32(stg);
    const uint32_t bars = sbase + A1_SM_BAR;
    const uint32_t bar_stat = bars + 64, bar_kv = bars + 72, bar_rd = bars + 168;
    const uint32_t bar_wo = bars + 208, bar_done = bars + 216, bar_pv = bars + 224, bar_kvf = bars + 232, bar_f2 = bars + 248, bar_e2 = bars + 384, que = bars + 448;
    const int tid = threadIdx.x;
    CSK(0);
    const int w = __shfl_sync(~0u, tid >> 5, 0), wg = w >> 2;
    uint32_t smid;
    asm volatile("mov.u32 %0, %smid;" : "=r"(smid));
    const uint4 tv = tab.e[(MAP ? smid : blockIdx.x) + (tid & (smid >> 12))];
    const bool one = elect();
    uint32_t tz;
    const unsigned char* wq;
    auto entry = [&] { tz = __shfl_sync(~0u, tv.z, 0); wq = (const unsigned char*)(((uint64_t)__shfl_sync(~0u, tv.y, 0) << 32) | __shfl_sync(~0u, tv.x, 0)); };
    auto issue_w = [&](unsigned it) { bulk_load(sbase + (it % A1_NST) * A1_STAGE + 16384, wq + it * WQ_STAGE, WQ_STAGE, bars + 8 * (it % A1_NST)); };
    auto issue_x = [&](unsigned it, int kb) {
        asm volatile("cp.async.bulk.tensor.5d.shared::cluster.global.mbarrier::complete_tx::bytes [%0], [%1, {%3, %3, %3, %4, %5}], [%2];"
                     ::"r"(sbase + (it % A1_NST) * A1_STAGE), "l"(&tmX), "r"(bars + 8 * (it % A1_NST)), "r"(0), "r"(tz & 15), "r"(kb) : "memory");
    };
    auto first_x = [&] {
        issue_x(0, (tz >> 16) & 7); issue_x(1, ((tz >> 16) & 7) + 1);
    };
    auto expect = [&] {
#pragma unroll
        for (int i = 0; i < A1_NST; i++) mbar_expect_tx(bars + 8 * i, A1_STAGE);
    };
    if (w == 8) {
        if (one) {
            prefetch_tmap(&tmX); prefetch_tmap(&tmW.q);
#pragma unroll
            for (int i = 0; i < A1_NST + 2; i++) mbar_init(bars + 8 * i - 16, 1);
            asm volatile("fence.mbarrier_init.release.cluster;" ::: "memory");
        }
        __syncwarp();
        asm volatile("bar.arrive 0, 384;" ::: "memory");
        if (smid >> 12) __trap();
        entry();
        if ((tz & 0x80000010u) == 16 && one) {
            issue_w(0);
            asm volatile("griddepcontrol.wait;" ::: "memory");
            first_x();
            issue_w(1);
            expect();
            asm volatile("griddepcontrol.launch_dependents;" ::: "memory");
        }
        __syncwarp();
        if (!(tz & 16) && blockIdx.x < 128) kgen_first(in, tmW, sbase + A1_SM_W0, bars - 16, one);
        __syncwarp();
    }
    if (w > 7) CSK(8);
    const bool gen = w != 8 && in.logA && blockIdx.x < 128;
    KgPar kp;
    const int w11 = w < 8 ? 2 * (w & 3) + (w >> 2) : w - 1;
    if (gen) kgen_load(in, w11, kp);
    if (w > 7) CSK(9);
    if (w == 8) {
        const int tile = tz >> 24, mb = tz & 15, hg = (tz >> 8) & 7, kb0 = (tz >> 16) & 7;
        const unsigned l1 = (tz >> 4) & 1;
        if (__builtin_expect(!l1, 0)) {
            CSK(1);
            const uint32_t ep = ld_epoch();
            if (one) kgen_side(in, sbase + A1_SM_W0, bars - 16, [&] { if (tile < 128) { first_x(); issue_x(2, kb0 + 2); expect(); } });
            __syncwarp();
            CSK(6);
            if (tile < 128) {
                await_all(32, ep * gridDim.x);
                if (one) { issue_w(0); issue_w(1); issue_w(2); }
            }
            CSK(7);
            asm volatile("bar.sync 3, 384;" ::: "memory");
            if (tile < 128 && one) {
                fence_async_smem();
                issue_x(3, kb0 + 3); issue_w(3);
                mbar_expect_tx(bars + 240, 20480);
                bulk_load(sbase + A1_SM_W0, in.x + (size_t)(mb * 128 + hg * 16) * DM, 20480, bars + 240);
            }
            __syncwarp();
            CSK(9);
        } else asm volatile("bar.sync 3, 64;" ::: "memory");
        if (tile < 128 && elect()) {
#pragma unroll 1
            for (unsigned kb = 4 - 2 * l1; kb < 10; kb++) {
                if (kb < A1_NST) mbar_wait(bars + 8 * A1_PW, 0);
                else {
                    mbar_wait(bars + 8 * (A1_NST + kb % A1_NST), ((kb / A1_NST) - 1) & 1);
                    if (l1 && kb < 9) mbar_wait(bar_rd + 8 * (kb - A1_NST), 0);
                    mbar_expect_tx(bars + 8 * (kb % A1_NST), A1_STAGE);
                }
                issue_x(kb, kb < 5 ? kb + kb0 : kb - kb0); issue_w(kb);
                CSK(6 + kb);
                if (kb == (l1 ? A1_WOAT : 9)) {
                    if (!l1) mbar_wait(bar_rd + 32, 0);
                    mbar_expect_tx(bar_wo, 8 * WOB);
                    bulk_load(sbase + A1_SM_W0, wo + hg * 8 * WOB, 2 * WOB, bar_wo);
                }
            }
            mbar_wait(bars + 8 * (A1_NST + 3), 1);
            bulk_load(sbase + A1_SM_W3, wo + (hg * 8 + 3) * WOB, 3 * WOB, bar_wo);
        }
        CSA(4); CSA_END;
        return;
    }
    {
        if (w < 8 && one) {
#pragma unroll 1
            for (uint32_t c = (w & 4 ? w & 2 ? 0x1111112'01111111ull : 0x1111111'01111184ull : w & 2 ? 0x3122222'01111111ull : 0x1111132'02220000ull) >> (32 * (w & 1)), b = bars + 56 * w; c; c >>= 4, b += 8)
                if (c & 15) mbar_init(b, c & 15);
            asm volatile("fence.mbarrier_init.release.cluster;" ::: "memory");
        }
        __syncwarp();
        asm volatile("bar.sync 0, 384;" ::: "memory");
        if (layer) {
            if (w == 9) asm volatile("bar.arrive 3, 64;" ::: "memory");
        } else {
            if (gen) { SPAN(0, 0); SPAN(0, 1); kgen_tables(in, reinterpret_cast<uint4*>(stg + 3 * A1_STAGE), w11, kp); }
            else if (w != 11 && w11 > 1) asm volatile("bar.arrive 9, 352;" ::: "memory");
            __syncwarp();
            if (w11 < 2) {
                kgen_sums(in, sbase + A1_SM_W0, bars - 16, w11);
                __syncwarp();
                asm volatile("bar.arrive 9, 352;" ::: "memory");
                CSK(1);
            }
            if (w == 9) asm volatile("bar.sync 3, 384;" ::: "memory"); else asm volatile("bar.arrive 3, 384;" ::: "memory");
        }
    }
    tz = __shfl_sync(~0u, tv.z, 0);
    const int tile = tz >> 24, mb = tz & 15, hg = (tz >> 8) & 7;
    float2* rst = reinterpret_cast<float2*>(stg + A1_SM_RS) + 8;
    if (wg == 2) {
        if (w == 11 && layer == 0) {
            asm volatile("bar.sync 9, 352;" ::: "memory");
            CSK(5);
            if (one) publish(64);
            __syncwarp();
            CSK(6);
        }
        if (tile >= 128) { sm_idle(layer); return; }
        if (w == 10) {
            if (one) { prefetch_tmap(&tmR); prefetch_tmap(&tmX1); }
            uint32_t ns;
            asm volatile("mov.u32 %0, %nsmid;" : "=r"(ns));
            if (MAP && ns != 132) __trap();
        }
        __syncwarp();
        if (w == 9) {
            uint4* pre = of + (mb * 8 + hg) * 1280 + (tid - 288);
#pragma unroll 1
            for (int k = 0; k < 10; k++) {
                if (k == (layer ? 0 : 5)) {
                    float4 a[2] = {};
#pragma unroll
                    for (int k = 0; k < 10; k++)
#pragma unroll
                        for (int h = 0; h < 2; h++) {
                            const int c4 = min(tid - 288 + 32 * h, 59);
                            const float4 v = __ldcg(reinterpret_cast<const float4*>(g_csp + (k / 5) * 9600 + (k % 5) * 640 + hg * 80) + c4 + (c4 / 20) * 780);
                            a[h].x += v.x; a[h].y += v.y; a[h].z += v.z; a[h].w += v.w;
                        }
#pragma unroll
                    for (int h = 0; h < 2; h++)
#pragma unroll
                        for (int k = 0; k < 4; k++) {
                            const float c = 0.5f * (k == 0 ? a[h].x : k == 1 ? a[h].y : k == 2 ? a[h].z : a[h].w), c1 = c - rbf(c), c2 = c1 - rbf(c1);
                            *reinterpret_cast<uint4*>(stg + A1_SM_XB + (4 * min(tid - 288 + 32 * h, 59) + k) * 16) = make_uint4(pack2(c, c1), pack2(c2, 0.f), 0u, 0u);
                        }
                    fence_async_smem();
                    __syncwarp();
                    if (tid == 288) mbar_arrive(bar_stat);
                    CSA(1);
                    if (!layer) break;
                }
#pragma unroll
                for (int i = 0; i < 8; i++) asm volatile("st.global.v4.u32 [%0], {%1,%1,%1,%1};" ::"l"(pre + 32 * i), "r"(~0u) : "memory");
                pre += k < 5 ? 256 : XCP / 8;
                if (k == 4) {
                    CSA(2);
                    asm volatile("fence.acq_rel.gpu;" ::: "memory");
                    asm volatile("fence.proxy.async.global;" ::: "memory");
                    __syncwarp();
                    if (tid == 288) mbar_arrive(bar_done);
                    CSA(3);
                    if (layer == 0) {
                        asm volatile("griddepcontrol.launch_dependents;" ::: "memory");
                        await_all(64, ld_epoch() * gridDim.x);
                        CSA(5);
                    }
                    pre = reinterpret_cast<uint4*>(g_yT) + tile * (5 * XCP / 8) + (tid - 288);
                }
            }
            TSTAMP1T(9, 288);
        } else {
            const int j = tid - 320;
            const uint32_t tag = ld_epoch();
            if (tid == 352) sm_started(layer);
            const int ch = j & 7, kg = (j >> 3) & 3;
            const unsigned char* src = stg + (layer ? (j >> 5) * 8192 + (hg & 3) * 2048 : A1_SM_W0 + (j >> 2) * 1280);
            const int of0 = layer ? kg * 128 + ((ch ^ kg) << 4) : (j & 7) << 4, ofx = layer ? 576 : 64, ofy = layer ? 1024 : 128;
            float s[8], q[8], p0[8];
#pragma unroll
            for (int i = 0; i < 8; i++) { s[i] = 0.f; q[i] = 0.f; }
#pragma unroll 1
            for (int it = 0; it < 5; it++) {
                uint4 v[4];
                mbar_wait(layer ? bars + 8 * (it % A1_NST) : bars + 240, layer * it / A1_NST);
#pragma unroll
                for (int k = 0; k < 4; k++) v[k] = *reinterpret_cast<const uint4*>(src + (layer ? (it % A1_NST) * A1_STAGE : it * 256) + (k & 1 ? of0 ^ ofx : of0) + (k >> 1) * ofy);
                if (it == 0) {
                    const uint4 pv = *reinterpret_cast<const uint4*>(src + (layer ? ch << 4 : 0));
                    const uint32_t w[4] = {pv.x, pv.y, pv.z, pv.w};
#pragma unroll
                    for (int i = 0; i < 4; i++) { p0[2 * i] = __uint_as_float((layer ? w[i] : w[0]) << 16); p0[2 * i + 1] = __uint_as_float(layer ? w[i] & 0xffff0000u : w[0] << 16); }
                }
                asm volatile("" :: "r"(v[0].x), "r"(v[1].x), "r"(v[2].x), "r"(v[3].x), "f"(p0[0]) : "memory");
                __syncwarp();
                if ((tid & 31) == 0) mbar_arrive(bar_rd + 8 * it);
#pragma unroll
                for (int k = 0; k < 4; k++) {
                    const uint32_t w[4] = {v[k].x, v[k].y, v[k].z, v[k].w};
#pragma unroll
                    for (int i = 0; i < 4; i++) {
                        const float a = __uint_as_float(w[i] << 16) - p0[2 * i], b = __uint_as_float(w[i] & 0xffff0000u) - p0[2 * i + 1];
                        s[2 * i] += a; s[2 * i + 1] += b; q[2 * i] = fmaf(a, a, q[2 * i]); q[2 * i + 1] = fmaf(b, b, q[2 * i + 1]);
                    }
                }
            }
            float o[4];
            int row;
            if (layer == 0) {
                float s0 = ((s[0] + s[1]) + (s[2] + s[3])) + ((s[4] + s[5]) + (s[6] + s[7])), q0 = ((q[0] + q[1]) + (q[2] + q[3])) + ((q[4] + q[5]) + (q[6] + q[7]));
#pragma unroll
                for (int o = 1; o <= 2; o <<= 1) { s0 += __shfl_xor_sync(~0u, s0, o); q0 += __shfl_xor_sync(~0u, q0, o); }
                if ((j & 3) == 0) {
                    const float d = s0 * (1.0f / DM);
                    const uint32_t ms = pack2(p0[0] + d, sqrt_apx(rbf(rbf(fmaxf(fmaf(-d, d, q0 * (1.0f / DM)), 0.f)) + 1e-5f)));
                    asm volatile("st.global.cg.u64 [%0], %1;" ::"l"(g_rstat + mb * 128 + (j & 4) * 16 + hg * 8 + (j >> 3)), "l"(tagw(ms, tag)) : "memory");
                    g_piv[mb * 128 + hg * 16 + ((j >> 2) & 8) + (j & 4) + ((j >> 3) & 3)] = __ushort_as_bfloat16((unsigned short)ms);
                }
                ulonglong2 v;
#pragma unroll 1
                for (int it = 0; it < SPIN_MAX; it++) {
                    v = ld_tag2(reinterpret_cast<const ulonglong2*>(g_rstat + mb * 128) + j);
                    if (tag_ok(v, tag)) break;
                    __nanosleep(100);
                }
                o[0] = __uint_as_float((uint32_t)v.x << 16); o[1] = rcp_apx(__uint_as_float((uint32_t)v.x & 0xffff0000u));
                o[2] = __uint_as_float((uint32_t)v.y << 16); o[3] = rcp_apx(__uint_as_float((uint32_t)v.y & 0xffff0000u));
                row = 2 * j;
            } else {
#pragma unroll
                for (int i = 0; i < 4; i++) {
                    const bool up = kg & 2;
                    const float ss = __shfl_xor_sync(~0u, up ? s[i] : s[i + 4], 16), qq = __shfl_xor_sync(~0u, up ? q[i] : q[i + 4], 16);
                    s[i] = (up ? s[i + 4] : s[i]) + ss; q[i] = (up ? q[i + 4] : q[i]) + qq; p0[i] = up ? p0[i + 4] : p0[i];
                }
#pragma unroll
                for (int i = 0; i < 2; i++) {
                    const bool up = kg & 1;
                    const float ss = __shfl_xor_sync(~0u, up ? s[i] : s[i + 2], 8), qq = __shfl_xor_sync(~0u, up ? q[i] : q[i + 2], 8);
                    s[i] = (up ? s[i + 2] : s[i]) + ss; q[i] = (up ? q[i + 2] : q[i]) + qq; p0[i] = up ? p0[i + 2] : p0[i];
                }
                uint4* gp = g_halo + 86016 + mb * 512 + j;
                const float d0 = s[0] * (1.0f / 80.0f), d1 = s[1] * (1.0f / 80.0f);
                asm volatile("st.relaxed.gpu.global.v4.f32 [%0], {%1,%2,%3,%4};" ::"l"(gp + hg * 64), "f"(p0[0] + d0), "f"(fmaxf(fmaf(-d0, s[0], q[0]), 0.f)), "f"(p0[1] + d1), "f"(fmaxf(fmaf(-d1, s[1], q[1]), 0.f)) : "memory");
                __nanosleep(ST_SLEEP0);
                uint32_t pw[8][4], todo = 0xff;
#pragma unroll 1
                for (int it = 0; it < SPIN_MAX; it++) {
#pragma unroll
                    for (int k = 0; k < 8; k++)
                        if (todo >> k & 1) asm volatile("ld.relaxed.gpu.global.v4.u32 {%0,%1,%2,%3}, [%4];" : "=r"(pw[k][0]), "=r"(pw[k][1]), "=r"(pw[k][2]), "=r"(pw[k][3]) : "l"(gp + k * 64) : "memory");
#pragma unroll
                    for (int k = 0; k < 8; k++)
                        if (__all_sync(~0u, pw[k][0] != ~0u && pw[k][1] != ~0u && pw[k][2] != ~0u && pw[k][3] != ~0u)) todo &= ~(1u << k);
                    if (!todo) break;
                    __nanosleep(ST_SLEEP);
                }
#pragma unroll
                for (int r = 0; r < 2; r++) {
                    float mean = 0.f, m2 = 0.f;
#pragma unroll
                    for (int k = 0; k < 8; k++) mean += __uint_as_float(pw[k][2 * r]);
                    mean *= 0.125f;
#pragma unroll
                    for (int k = 0; k < 8; k++) {
                        const float dm = __uint_as_float(pw[k][2 * r]) - mean;
                        m2 += fmaf(80.0f * dm, dm, __uint_as_float(pw[k][2 * r + 1]));
                    }
                    o[2 * r] = rbf(mean);
                    o[2 * r + 1] = rcp_apx(rbf(sqrt_apx(rbf(rbf(m2 * (1.0f / DM)) + 1e-5f))));
                }
                row = (j >> 5) * 64 + (j & 7) * 8 + ((j >> 3) & 3) * 2;
                if (hg == 0) *reinterpret_cast<uint32_t*>(g_piv + SEQ + mb * 128 + 2 * (row & 60) + 4 * (row >> 6) + (row & 3)) = __byte_perm(__float_as_uint(o[0]), __float_as_uint(o[2]), 0x7632);
            }
#pragma unroll
            for (int r = 0; r < 2; r++)
                *reinterpret_cast<uint4*>(stg + A1_SM_XA + (row + r) * 16) = make_uint4(__byte_perm(__float_as_uint(-o[2 * r]), 0, 0x3232), __float_as_uint(-o[2 * r]) >> 16, 0u, 0u);
            *reinterpret_cast<float4*>(rst + row + (row >> 6) * 8) = make_float4(o[0], o[1], o[2], o[3]);
            fence_async_smem();
            TSTAMP1T(7, 320); CSA(1);
            if (tid == 320) DBGC(44);
            __syncwarp();
            if ((tid & 31) == 0) mbar_arrive(bar_stat);
        }
        CSA(4); CSA_END;
        if (tid == 320) DBGCAL(0);
        if (tid == WOT) {
            mbar_wait(WO_LATE, 0);
            mbar_wait(bar_done, 0);
            bulk_load(sbase, wo + (hg * 8 + 6) * WOB, 2 * WOB, bar_wo);
            bulk_load(sbase + A1_SM_W0 + 2 * WOB, wo + (hg * 8 + 2) * WOB, WOB, bar_wo);
        }
        __syncwarp();
#define FWA 11
#define FWB 10
        if (w == FWA || w == FWB) {
            const int cw = w == FWB;
            const uint32_t* fl = reinterpret_cast<const uint32_t*>(rsum + 2 * SEQ) + (((layer * 16 + mb) * 2 + cw) * 8 + (tid & 7)) * FSTR;
            const unsigned char* src = reinterpret_cast<const unsigned char*>(of) + mb * 163840 + cw * 10240 + (tid & 7) * 20480;
            const uint32_t sl = sbase + (cw ? A1_SM_A1 : A1_SM_A0);
            mbar_wait(cw ? bar_done : bar_kvf, 0);
            if ((tid & 31) == 0) {
                mbar_expect_tx(bar_f2 + 64 * cw + 64, 10240);
                tma_load_3d(sl + 51200, &tmR, layer ? 0 : hg * 80, layer ? hg * 80 : mb * 64, layer ? mb * 2 + cw : cw, bar_f2 + 64 * cw + 64);
            }
            __syncwarp();
            uint32_t pend = 0xffu & ~(1u << hg), v = 0;
            const uint32_t bo = wo_off((tid & 7) + ((tid & 7) < hg)) >> 4, lt = (1u << (tid & 31)) - 1;
#pragma unroll 1
            for (int it = 0; pend && it < 2 * SPIN_MAX; it++) {
                if (v != 4 && (pend >> (tid & 31) & 1)) asm volatile(A1_FLD " %0, [%1];" : "=r"(v) : "l"(fl) : "memory");
                uint32_t fr;
                asm volatile("{\n.reg .pred p;\nmbarrier.test_wait.parity.shared::cta.b64 p, [%1], 0;\nselp.b32 %0, 1, 0, p;\n}" : "=r"(fr) : "r"(bar_e2 + 16 * cw + (tid & 1) * 8) : "memory");
                fr = __ballot_sync(~0u, fr);
                uint32_t m = __ballot_sync(~0u, v == 4 || it >= A1_FSPIN) & pend;
                const int q = 8 - __popc(pend) + __popc(m & lt);
                m &= __ballot_sync(~0u, q < ((fr & 2) ? 8 : (fr & 1) ? 7 : 5));
                pend ^= m;
                if (m >> (tid & 31) & 1) DBGC(12 + cw * 8 + (tid & 7));
                if (!m) __nanosleep(A1_FSLEEP);
                else asm volatile("fence.proxy.async.global;" ::: "memory");
                if (m >> (tid & 31) & 1) {
                    bulk_load(q == 7 && !cw ? sbase + A1_SM_W0 : sl + (q < 6 ? q : q - 6) * 10240, src, 10240, bar_f2 + 64 * cw + 8 * q);
                    asm volatile("st.shared.u32 [%0], %1;" ::"r"(que + 32 * cw + 4 * q), "r"(bo) : "memory");
                    mbar_expect_tx(bar_f2 + 64 * cw + 8 * q, 10240);
                    DBGC(44 + cw * 8 + q);
                }
                __syncwarp();
            }
        }
    } else if (tile < 128) {
        SPAN(1 + 4 * layer, 0);
        constexpr int on = 1;
        float acc[120];
        const int lane = tid & 31, warp = w & 7, g = lane >> 2, t = lane & 3;
        if (on) {
            SPAN(1 + 4 * layer, 1);
            TSTAMP1(0);
            if (threadIdx.x == 0) { GSTAMP(g_tim1, 15); }
            TSTAMP3(0);
            if (tid == 0) TSTAMP2(0);
            TSTAMP4(0);
            if (tid == 0) DBGC(60);
            if (layer == 0) a1_mainloop<0>(acc, sbase, bars, wg, tile); else a1_mainloop<1>(acc, sbase, bars, wg, tile);
            uint32_t ok;
            asm volatile("{\n.reg .pred p;\nmbarrier.test_wait.parity.shared::cta.b64 p, [%1], 0;\nselp.b32 %0, 1, 0, p;\n}" : "=r"(ok) : "r"(bar_stat) : "memory");
            if (tid == 128 && !ok) mbar_arrive(bars + 160);
            __syncwarp();
            mbar_wait(bar_stat, 0);
            wgmma_fence();
            wgmma_n240<0, 0>(acc, make_desc(sbase + A1_SM_XA + wg * 1024, 0, 128, 0), make_desc(sbase + A1_SM_XB, 0, 128, 0), 1);
            wgmma_commit();
            if (tid == 128 && ok) mbar_arrive(bars + 160);
            mbar_wait(bars + 8 * (A1_NST + 3), 1);
        }
        const float2* rw = rst + 16 * warp + 8 * wg;
        const float rb0 = rw[g + 8].y, ra = rw[g].y * 0.22360679774997896f, rb = rb0 * 0.22360679774997896f;
        wgmma_wait<0>();
        if ((tid & 127) == 0) mbar_arrive(bar_done);
        TSTAMP1(2); CSA(1);
        TSTAMP1T(13, 224);
        if ((tid & 127) == 0) DBGC(62 - wg);
        uint32_t f[2][30];
#pragma unroll
        for (int j = 10; j < 30; j++) f[1][j] = pack2(acc[4 * j + 2], acc[4 * j + 3]);
        if ((warp & 3) == 3) {
            uint4* hout = g_halo + (((layer * 16 + mb) * 8 + hg) * 2 + wg) * 168;
#pragma unroll
            for (int j = 0; j < 20; j += 4)
                asm volatile("st.relaxed.gpu.global.v4.u32 [%0], {%1,%2,%3,%4};" ::"l"(hout + 8 * j + lane), "r"(f[1][10 + j]), "r"(f[1][11 + j]), "r"(f[1][12 + j]), "r"(f[1][13 + j]) : "memory");
            if (t == 0) asm volatile("st.relaxed.gpu.global.f32 [%0], %1;" ::"l"(reinterpret_cast<float*>(hout + 160) + g), "f"(rb0) : "memory");
        }
        TSTAMP1T(12, 224);
        const uint32_t kvw = sbase + A1_SM_KV + (16 * warp + 8 * wg) * A1_KVP;
        const uint32_t mrow = kvw + (lane & 7) * A1_KVP + (lane >> 3) * 16;
#pragma unroll
        for (int j = 0; j < 20; j += 4) stsm_x4(mrow + 16 * A1_KVP + 16 * j, f[1][10 + j], f[1][11 + j], f[1][12 + j], f[1][13 + j]);
        __syncwarp();
        if (lane == 0 && (warp & 3) != 3) mbar_arrive(bar_kv + 8 * (warp + 1));
#pragma unroll
        for (int j = 0; j < 30; j++) f[0][j] = pack2(acc[4 * j], acc[4 * j + 1]);
        stsm_x4(mrow + 8 * A1_KVP + 160, f[0][20], f[0][21], f[0][22], f[0][23]);
        stsm_x4(mrow + 8 * A1_KVP + 224, f[0][24], f[0][25], f[0][26], f[0][27]);
        asm volatile("stmatrix.sync.aligned.m8n8.x2.shared.b16 [%0], {%1,%2};" ::"r"(mrow + 8 * A1_KVP + 288), "r"(f[0][28]), "r"(f[0][29]) : "memory");
#pragma unroll
        for (int j = 0; j < 10; j++) f[1][j] = pack2(acc[4 * j + 2], acc[4 * j + 3]);
        __syncwarp();
        uint32_t vb[10][2], vp[12], kp[12];
#pragma unroll
        for (int j = 0; j < 10; j += 2) ldsm_x4_t(&vb[j][0], kvw + (8 + (lane & 15)) * A1_KVP + 160 + (lane >> 4) * 16 + 16 * j);
        const bool up0 = 2 * t > g, up1 = 2 * t + 1 > g, edge = (mb | (warp & 3)) == 0;
        float rk[4];
        auto above = [&]() {
            mbar_wait(bar_kv + 8 * warp, 0);
#pragma unroll
            for (int j = 0; j < 12; j += 4) ldsm_x4(&kp[j], mrow + 16 * j);
            rk[0] = rw[2 * t - (up0 ? 8 : 0)].y; rk[1] = rw[2 * t + 1 - (up1 ? 8 : 0)].y;
#pragma unroll
            for (int j = 0; j < 12; j += 4) ldsm_x4_t(&vp[j], mrow + 160 + 16 * j - (j == 8 ? (lane & 16) * 2 : 0));
            __syncwarp();
            if (lane == 0) mbar_arrive(bar_kvf);
        };
        auto halo = [&]() {
            if (lane == 0) mbar_arrive(bar_kvf);
            const uint4* hin = g_halo + (((layer * 16 + mb - 1) * 8 + hg) * 2 + wg) * 168;
            uint32_t hv[22] = {};
            rk[0] = rw[2 * t].y; rk[1] = rw[2 * t + 1].y;
            if (mb > 0) {
#pragma unroll 1
                for (int it = 0; it < SPIN_MAX; it++) {
#pragma unroll
                    for (int k = 0; k < 20; k += 4)
                        asm volatile("ld.relaxed.gpu.global.v4.u32 {%0,%1,%2,%3}, [%4];" : "=r"(hv[k]), "=r"(hv[k + 1]), "=r"(hv[k + 2]), "=r"(hv[k + 3]) : "l"(hin + 8 * k + lane) : "memory");
                    asm volatile("ld.relaxed.gpu.global.v2.u32 {%0,%1}, [%2];" : "=r"(hv[20]), "=r"(hv[21]) : "l"(reinterpret_cast<const uint2*>(hin + 160) + t) : "memory");
                    uint32_t m = max(hv[20], hv[21]);
#pragma unroll
                    for (int k = 0; k < 20; k += 2) m = __vimax3_u32(m, hv[k], hv[k + 1]);
                    if (!__any_sync(~0u, m == ~0u)) break;
                }
            }
            if (lane == 0) DBGC(52 - 16 * wg);
#pragma unroll
            for (int j = 0; j < 10; j++) {
                kp[j] = hv[j];
                asm volatile("movmatrix.sync.aligned.m8n8.trans.b16 %0, %1;" : "=r"(vp[j]) : "r"(hv[10 + j]));
            }
            if (up0) rk[0] = __uint_as_float(hv[20]);
            if (up1) rk[1] = __uint_as_float(hv[21]);
        };
        rk[2] = rw[2 * t + (up0 ? 0 : 8)].y; rk[3] = rw[2 * t + 1 + (up1 ? 0 : 8)].y;
        uint32_t qs[4][2];
#pragma unroll
        for (int h = 0; h < 4; h++) {
            qs[h][0] = (t >> 1) == (h & 1) ? f[0][5 * (h >> 1) + 2] : 0u; qs[h][1] = (t >> 1) == (h & 1) ? f[1][5 * (h >> 1) + 2] : 0u;
            asm volatile("" : "+r"(qs[h][0]), "+r"(qs[h][1]));
        }
#pragma unroll
        for (int j = 0; j < 10; j++) asm volatile("" : "+r"(f[0][j]), "+r"(f[1][j]), "+r"(f[0][10 + j]));
        if (warp & 3) above(); else if (wg) halo();
        TSTAMP1T(10, 64); CSA(2);
        if (warp && !wg) mbar_wait(bars + 416 + 8 * warp, 0);
        CSA(3);
        float sc[4][3][4];
#pragma unroll
        for (int h = 0; h < 4; h++) {
            const int jb = 5 * (h >> 1) + 3 * (h & 1), js = 5 * (h >> 1) + 2;
#pragma unroll
            for (int nt = 1; nt < 3; nt++) {
#pragma unroll
                for (int e = 0; e < 4; e++) sc[h][nt][e] = 0.f;
                mma_bf16(sc[h][nt], f[0][jb], f[1][jb], f[0][jb + 1], f[1][jb + 1], f[nt - 1][10 + jb], f[nt - 1][11 + jb]);
                mma_bf16_k8(sc[h][nt], qs[h][0], qs[h][1], f[nt - 1][10 + js]);
            }
        }
        if (warp == 0) halo();
        TSTAMP1(8); CSA(4);
#pragma unroll
        for (int h = 0; h < 4; h++) {
            const int jb = 5 * (h >> 1) + 3 * (h & 1), js = 5 * (h >> 1) + 2;
#pragma unroll
            for (int e = 0; e < 4; e++) sc[h][0][e] = 0.f;
            mma_bf16(sc[h][0], f[0][jb], f[1][jb], f[0][jb + 1], f[1][jb + 1], kp[jb], kp[jb + 1]);
            mma_bf16_k8(sc[h][0], qs[h][0], qs[h][1], kp[js]);
        }
        TSTAMP1T(3, 64);
        float p[4][4], sum[4][2];
        uint32_t lg[4][2], mx[4];
        const float rl[4] = {rk[0] * ra, rk[1] * ra, rk[2] * rb, rk[3] * rb};
        auto max2 = [](uint32_t a, uint32_t b) { uint32_t r; asm("max.bf16x2 %0, %1, %2;" : "=r"(r) : "r"(a), "r"(b)); return r; };
#pragma unroll
        for (int h = 0; h < 4; h++) {
            lg[h][0] = pack2((up0 ? sc[h][0][0] : sc[h][1][0]) * rl[0], (up0 ? sc[h][1][2] : sc[h][2][2]) * rl[2]);
            lg[h][1] = pack2((up1 ? sc[h][0][1] : sc[h][1][1]) * rl[1], (up1 ? sc[h][1][3] : sc[h][2][3]) * rl[3]);
            if (edge) {
                if (up0) lg[h][0] = __byte_perm(lg[h][0], 0xce6eu, 0x3254);
                if (up1) lg[h][1] = __byte_perm(lg[h][1], 0xce6eu, 0x3254);
            }
            mx[h] = max2(lg[h][0], lg[h][1]);
        }
#pragma unroll
        for (int o = 1; o <= 2; o <<= 1)
#pragma unroll
            for (int h = 0; h < 4; h++) mx[h] = max2(mx[h], __shfl_xor_sync(~0u, mx[h], o));
#pragma unroll
        for (int h = 0; h < 4; h++)
#pragma unroll
            for (int r = 0; r < 2; r++) {
                const float m = __uint_as_float(r ? mx[h] & 0xffff0000u : mx[h] << 16);
#pragma unroll
                for (int e = 0; e < 2; e++)
                    asm("ex2.approx.ftz.f32 %0, %1;" : "=f"(p[h][2 * r + e]) : "f"((__uint_as_float(r ? lg[h][e] & 0xffff0000u : lg[h][e] << 16) - m) * 1.4426950408889634f));
                sum[h][r] = p[h][2 * r] + p[h][2 * r + 1];
            }
#pragma unroll
        for (int o = 1; o <= 2; o <<= 1)
#pragma unroll
            for (int h = 0; h < 4; h++)
#pragma unroll
                for (int r = 0; r < 2; r++) sum[h][r] += __shfl_xor_sync(~0u, sum[h][r], o);
        TSTAMP1T(5, 64); CSA(5);
        const uint32_t mu = (up0 ? 0xffffu : 0u) | (up1 ? 0xffff0000u : 0u);
        uint32_t ob[10][2];
#pragma unroll
        for (int P = 0; P < 2; P++) {
            float os[2][4];
#pragma unroll
            for (int e = 0; e < 2; e++) {
                const int h = 2 * P + e;
                const float i0 = rcp_apx(sum[h][0]), i1 = rcp_apx(sum[h][1]);
                const uint32_t w0 = pack2(p[h][0] * rk[0] * i0, p[h][1] * rk[1] * i0), w1 = pack2(p[h][2] * rk[2] * i1, p[h][3] * rk[3] * i1);
#pragma unroll
                for (int dt = 0; dt < 3; dt++) {
                    const int j = 5 * P + (dt < 2 ? 3 * e + dt : 2);
                    float o[4] = {0.f, 0.f, 0.f, 0.f};
                    mma_bf16(o, w0 & ~mu, w1 & mu, 0u, w1 & ~mu, vb[j][0], vb[j][1]);
                    mma_bf16_k8(o, w0 & mu, 0u, vp[j]);
                    if (dt < 2) { ob[j][0] = pack2(o[0], o[1]); ob[j][1] = pack2(o[2], o[3]); }
                    else { os[e][0] = o[0]; os[e][1] = o[1]; os[e][2] = o[2]; os[e][3] = o[3]; }
                }
            }
#pragma unroll
            for (int k = 0; k < 4; k++) os[0][k] = t < 2 ? os[0][k] : os[1][k];
            ob[5 * P + 2][0] = pack2(os[0][0], os[0][1]); ob[5 * P + 2][1] = pack2(os[0][2], os[0][3]);
        }
        const uint32_t sl = sbase + (wg ? A1_SM_A1 : A1_SM_A0);
        const uint32_t o0 = (warp & 3) * 2048 + g * 64 + ((t ^ (g >> 1)) << 4), o1 = 8192 + (warp & 3) * 512 + g * 32 + ((t ^ ((g >> 2) << 1)) << 3);
        CSA(15);
        mbar_wait(bar_done, 0);
        if (wg == 0) mbar_wait(bar_kvf, 0);
#pragma unroll
        for (int h = 0; h < 2; h++) {
            asm volatile("st.shared.v4.u32 [%0], {%1,%2,%3,%4};" ::"r"(sl + o0 + h * 1024), "r"(ob[0][h]), "r"(ob[1][h]), "r"(ob[2][h]), "r"(ob[3][h]) : "memory");
            asm volatile("st.shared.v4.u32 [%0], {%1,%2,%3,%4};" ::"r"(sl + o0 + h * 1024 + 512), "r"(ob[4][h]), "r"(ob[5][h]), "r"(ob[6][h]), "r"(ob[7][h]) : "memory");
            asm volatile("st.shared.v2.u32 [%0], {%1,%2};" ::"r"(sl + o1 + h * 256), "r"(ob[8][h]), "r"(ob[9][h]) : "memory");
        }
        if (wg && lane == 0) mbar_arrive(bars + 384 + 8 * warp);
        fence_async_smem();
        __syncwarp();
        TSTAMP1T(4, 64); CSA(6);
        TSTAMP1(1);
        TSTAMP2(1);
        const unsigned char* ot = reinterpret_cast<const unsigned char*>(of) + mb * 163840 + wg * 10240;
        if (lane == 0) {
            asm volatile("cp.async.bulk.global.shared::cta.bulk_group [%0], [%1], 2048;" ::"l"(ot + hg * 20480 + (warp & 3) * 2048), "r"(sl + (warp & 3) * 2048) : "memory");
            asm volatile("cp.async.bulk.global.shared::cta.bulk_group [%0], [%1], 512;" ::"l"(ot + hg * 20480 + 8192 + (warp & 3) * 512), "r"(sl + 8192 + (warp & 3) * 512) : "memory");
            asm volatile("cp.async.bulk.commit_group;" ::: "memory");
            if (wg == 0) mbar_arrive(bar_pv);
            asm volatile("cp.async.bulk.wait_group 0;" ::: "memory");
            asm volatile(A1_FRED " [%0], 1;" ::"l"(reinterpret_cast<uint32_t*>(rsum + 2 * SEQ) + (((layer * 16 + mb) * 2 + wg) * 8 + hg) * FSTR) : "memory");
            DBGC(4 + warp);
        }
        TSTAMP4(11); CSA(7);
        float ac2[40];
        const uint64_t db0 = make_desc(sbase, 1024, 256, 3), db1 = make_desc(sbase + 10240, 512, 256, 3), da0 = make_desc(sl, 16, 1024, 2), da1 = make_desc(sl + 8192, 16, 256, 3);
        const uint32_t o7 = wg ? 640 : (A1_SM_W0 - A1_SM_A0) >> 4;
        const uint32_t trow = ((lane & 7) + 8 * (lane >> 4)) * 128 + (((2 * (warp & 3) + ((lane >> 3) & 1)) ^ (lane & 7)) << 4);
        uint32_t xr[10][2];
        mbar_wait(bar_f2 + 64 * wg + 64, 0);
        if (layer == 0) {
#pragma unroll
            for (int j = 0; j < 10; j += 2) ldsm_x4(&xr[j][0], sl + 51200 + (16 * (warp & 3) + (lane & 15)) * 160 + (lane >> 4) * 16 + 16 * j);
        } else {
#pragma unroll
            for (int j = 0; j < 10; j += 2) ldsm_x4_t(&xr[j][0], sl + 51200 + trow + 1024 * j);
        }
        const uint32_t ri = __shfl_sync(~0u, layer * SEQ + (wg * 2 + ((g >> 1) & 1)) * 512 + (mb * 16 + 4 * (warp & 3) + (g >> 2)) * 2 + (g & 1), lane);
        mbar_wait(bar_wo, 0);
        if (wg) mbar_wait(bar_pv, 0);
        if (wg) asm volatile("bar.sync 2, 128;" ::: "memory"); else asm volatile("bar.sync 1, 128;" ::: "memory");
        TSTAMP2(2); CSA(8);
#pragma unroll
        for (int q = 0; q < 8; q++) {
            uint32_t bo = wo_off(0) >> 4;
            if (q) {
                mbar_wait(bar_f2 + 64 * wg + 8 * q, 0);
                asm volatile("ld.shared.u32 %0, [%1];" : "=r"(bo) : "r"(que + 32 * wg + 4 * q) : "memory");
                bo = __shfl_sync(~0u, bo, 0);
                TSTAMP4(q);
                if (q % 3 == 1) CSA(9 + q / 3);
                if (q == 1 && (tid & 127) == 0) DBGC(29 + 8 * wg);
            }
            wgmma_fence();
#pragma unroll
            for (int j = 0; j < 5; j++) wgmma_n80(ac2, (j < 4 ? da0 : da1) + (q == 7 ? o7 : 0u) + (uint64_t)((q < 6 ? q * 640 : 0) + (j & 2) * 16 + (j & 1) * 2), (j < 4 ? db0 : db1) + bo + (uint64_t)((j & 2) * 160 + (j & 1) * 32), j || q);
            wgmma_commit();
            if (q == 0) {
                wgmma_wait<0>();
                if ((tid & 127) == 0) { mbar_arrive(bar_e2 + 16 * wg); mbar_arrive(bar_e2 + 8); }
            }
            if (q == 2 && wg) {
                wgmma_wait<1>();
                if (tid == 128) mbar_arrive(bar_e2 + 24);
            }
        }
        if ((tid & 127) == 0) DBGC(28 + wg * 8 + 7);
        TSTAMP2(3);
        wgmma_wait<0>();
        TSTAMP2(4); CSA(12);
        if (__any_sync(~0u, ac2[0] != ac2[0] || ac2[2] != ac2[2])) {
#pragma unroll
            for (int i = 0; i < 40; i++) ac2[i] = 0.f;
            uint32_t a[20], an[20];
            auto lda = [&](uint32_t (&r)[20], int h) {
#pragma unroll
                for (int u = 0; u < 4; u++)
                    asm volatile("ld.relaxed.gpu.global.v4.u32 {%0,%1,%2,%3}, [%4];" : "=r"(r[4 * u]), "=r"(r[4 * u + 1]), "=r"(r[4 * u + 2]), "=r"(r[4 * u + 3]) : "l"(ot + h * 20480 + o0 + u * 512) : "memory");
#pragma unroll
                for (int u = 0; u < 2; u++)
                    asm volatile("ld.relaxed.gpu.global.v2.u32 {%0,%1}, [%2];" : "=r"(r[16 + 2 * u]), "=r"(r[17 + 2 * u]) : "l"(ot + h * 20480 + o1 + u * 256) : "memory");
            };
            lda(an, 0);
#pragma unroll 5
            for (int k = lane; k < WOB / 16; k += 32)
                reinterpret_cast<uint4*>(stg + (sl - sbase))[k] = __ldcg(reinterpret_cast<const uint4*>(wo + hg * 8 * WOB) + k);
            __syncwarp();
#pragma unroll 1
            for (int h = 0; h < 8; h++) {
#pragma unroll 1
                for (int it = 0; it < SPIN_MAX; it++) {
                    uint32_t m = 0;
#pragma unroll
                    for (int k = 0; k < 20; k += 2) m = __vimax3_u32(m, an[k], an[k + 1]);
                    if (!__any_sync(~0u, m == ~0u)) break;
                    lda(an, h);
                }
#pragma unroll
                for (int k = 0; k < 20; k++) a[k] = an[k];
                lda(an, min(h + 1, 7));
                const uint32_t bp = h == hg ? sl : sbase + wo_off(h + (h < hg));
                const int r0 = 8 * ((lane & 7) >> 1) + 2 * (lane >> 3) + (lane & 1), r2 = 4 * ((lane & 7) >> 1) + 2 * ((lane >> 3) & 1) + (lane & 1);
#pragma unroll
                for (int n = 0; n < 10; n++) {
                    uint32_t b[12];
                    ldsm_x4_t(b, bp + (n >> 1) * 1024 + r0 * 32 + (((n ^ (r0 >> 2)) & 1) << 4));
                    ldsm_x4_t(b + 4, bp + 5120 + (n >> 1) * 1024 + r0 * 32 + (((n ^ (r0 >> 2)) & 1) << 4));
                    ldsm_x4_t(b + 8, bp + 10240 + (n >> 1) * 512 + r2 * 32 + (((n ^ (r2 >> 2)) & 1) << 4));
                    mma_bf16(ac2 + 4 * n, a[0], a[8], a[1], a[9], b[0], b[1]); mma_bf16(ac2 + 4 * n, a[2], a[10], a[3], a[11], b[2], b[3]);
                    mma_bf16(ac2 + 4 * n, a[4], a[12], a[5], a[13], b[4], b[5]); mma_bf16(ac2 + 4 * n, a[6], a[14], a[7], a[15], b[6], b[7]);
                    mma_bf16(ac2 + 4 * n, a[16], a[18], a[17], a[19], b[8], b[9]);
                }
            }
        }
#pragma unroll
        for (int j = 0; j < 10; j++)
#pragma unroll
            for (int hh = 0; hh < 2; hh++) {
                const uint32_t a = pack2(ac2[4 * j + 2 * hh], ac2[4 * j + 2 * hh + 1]);
                const __nv_bfloat162 r = __hadd2_rn(*reinterpret_cast<const __nv_bfloat162*>(&xr[j][hh]), *reinterpret_cast<const __nv_bfloat162*>(&a));
                xr[j][hh] = *reinterpret_cast<const uint32_t*>(&r);
            }
        const uint32_t so = sl + 30720;
#pragma unroll
        for (int j = 0; j < 10; j += 2) stsm_x4_t(so + trow + 1024 * j, xr[j][0], xr[j][1], xr[j + 1][0], xr[j + 1][1]);
        if (wg) asm volatile("bar.sync 2, 128;" ::: "memory"); else asm volatile("bar.sync 1, 128;" ::: "memory");
        TSTAMP2(5); CSA(13);
        if ((tid & 127) == 0) {
            fence_async_smem();
            asm volatile("cp.async.bulk.tensor.2d.global.shared::cta.bulk_group [%0, {%1, %2}], [%3];" ::"l"(&tmX1), "r"(mb * 128 + 64 * wg), "r"(hg * 80), "r"(so) : "memory");
            asm volatile("cp.async.bulk.commit_group;" ::: "memory");
        }
        __syncwarp();
        const float p0 = *(volatile const float*)&rw[g].x, p1 = *(volatile const float*)&rw[g + 8].x;
        float s[3][4] = {};
        const uint32_t pp[2] = {__byte_perm(__float_as_uint(p0), 0, 0x3232), __byte_perm(__float_as_uint(p1), 0, 0x3232)};
#pragma unroll
        for (int j = 0; j < 10; j += 2) {
            const uint32_t d0 = sub2(xr[j][0], pp[0]), d1 = sub2(xr[j][1], pp[1]), d2 = sub2(xr[j + 1][0], pp[0]), d3 = sub2(xr[j + 1][1], pp[1]);
            mma_bf16(s[0], xr[j][0], xr[j][1], xr[j + 1][0], xr[j + 1][1], 0x3f803f80u, 0x3f803f80u);
            mma_bf16(s[1], d0, d1, d2, d3, d0, d2);
            mma_bf16(s[2], d0, d1, d2, d3, d1, d3);
        }
        if (t == (g >> 1)) {
            float2* rp = rsum + ri;
            asm volatile("red.relaxed.gpu.global.add.v2.f32 [%0], {%1, %2};" ::"l"(rp), "f"(fmaf(-80.f, p0, s[0][0])), "f"((g & 1) ? s[1][1] : s[1][0]) : "memory");
            asm volatile("red.relaxed.gpu.global.add.v2.f32 [%0], {%1, %2};" ::"l"(rp + 4), "f"(fmaf(-80.f, p1, s[0][2])), "f"((g & 1) ? s[2][3] : s[2][2]) : "memory");
        }
        asm volatile("cp.async.bulk.wait_group.read 0;" ::: "memory");
        TSTAMP2(6); CSA(14); CSA_END;
        if (tid == 0) DBGC(63);
        if (tid == 128) DBGC(28);
        if (tid == 0) DBGCAL(2);
        GSTAMP(g_tim1, 14);
        SPAN(1 + 4 * layer, 3);
    }
#undef layer
}

static int h_nsm;
static void* h_sym[11];
static TileTab h_tab[2];
static CUtensorMap h_tmX0, h_tmX1, h_tmR0, h_tmR1, h_tmX1st, h_tmOut;
static KgMaps h_tmW;
typedef CUresult (*PFN_encodeTiled)(CUtensorMap*, CUtensorMapDataType, cuuint32_t, void*, const cuuint64_t*, const cuuint64_t*,
                                    const cuuint32_t*, const cuuint32_t*, CUtensorMapInterleave, CUtensorMapSwizzle,
                                    CUtensorMapL2promotion, CUtensorMapFloatOOBfill);
static void make_tmap(CUtensorMap* tm, const void* ptr, uint64_t cols, uint64_t rows, uint32_t bc, uint32_t br, CUtensorMapSwizzle sw, uint64_t pitch = 0, uint64_t hi = 0, uint32_t bh = 2) {
    static PFN_encodeTiled fn = nullptr;
    if (!fn) {
        void* p = nullptr; cudaDriverEntryPointQueryResult qr;
        cudaGetDriverEntryPoint("cuTensorMapEncodeTiled", &p, cudaEnableDefault, &qr);
        fn = (PFN_encodeTiled)p;
    }
    if (br == 0) {
        cuuint64_t dims[5] = {16, 2, rows / 8, 4, cols / 16}; cuuint64_t strides[4] = {cols * 2, cols * 16, cols * 4, 32};
        cuuint32_t box[5] = {16, 2, bc, 4, 5}; cuuint32_t es[5] = {1, 1, 1, 1, 1};
        fn(tm, CU_TENSOR_MAP_DATA_TYPE_BFLOAT16, 5, const_cast<void*>(ptr), dims, strides, box, es, CU_TENSOR_MAP_INTERLEAVE_NONE, sw,
           CU_TENSOR_MAP_L2_PROMOTION_L2_128B, CU_TENSOR_MAP_FLOAT_OOB_FILL_NONE);
        return;
    }
    if (hi == 16) {
        cuuint64_t dims[4] = {16, 32, 120, 20}; cuuint64_t strides[3] = {3840, 32, 32 * 3840};
        cuuint32_t box[4] = {16, 32, 5, 2}; cuuint32_t es[4] = {1, 1, 1, 1};
        fn(tm, CU_TENSOR_MAP_DATA_TYPE_BFLOAT16, 4, const_cast<void*>(ptr), dims, strides, box, es, CU_TENSOR_MAP_INTERLEAVE_NONE, sw,
           CU_TENSOR_MAP_L2_PROMOTION_L2_128B, CU_TENSOR_MAP_FLOAT_OOB_FILL_NONE);
        return;
    }
    if (bh == 0) {
        cuuint64_t dims[5] = {64, 64, 2, 16, 10}; cuuint64_t strides[4] = {pitch * 2, hi * 2, cols * 2, rows * 2};
        cuuint32_t box[5] = {64, 64, 2, 1, 1}; cuuint32_t es[5] = {1, 1, 1, 1, 1};
        fn(tm, CU_TENSOR_MAP_DATA_TYPE_BFLOAT16, 5, const_cast<void*>(ptr), dims, strides, box, es, CU_TENSOR_MAP_INTERLEAVE_NONE, sw,
           CU_TENSOR_MAP_L2_PROMOTION_L2_128B, CU_TENSOR_MAP_FLOAT_OOB_FILL_NONE);
        return;
    }
    if (hi) {
        cuuint64_t dims[3] = {cols, rows, hi == 64 ? 32u : 2u}; cuuint64_t strides[2] = {pitch * 2, hi * 2};
        cuuint32_t box[3] = {bc, br, bh}; cuuint32_t es[3] = {1, 1, 1};
        fn(tm, CU_TENSOR_MAP_DATA_TYPE_BFLOAT16, 3, const_cast<void*>(ptr), dims, strides, box, es, CU_TENSOR_MAP_INTERLEAVE_NONE, sw,
           CU_TENSOR_MAP_L2_PROMOTION_L2_128B, CU_TENSOR_MAP_FLOAT_OOB_FILL_NONE);
        return;
    }
    cuuint64_t dims[2] = {cols, rows}; cuuint64_t strides[1] = {(pitch ? pitch : cols) * 2};
    cuuint32_t box[2] = {bc, br}; cuuint32_t es[2] = {1, 1};
    fn(tm, CU_TENSOR_MAP_DATA_TYPE_BFLOAT16, 2, const_cast<void*>(ptr), dims, strides, box, es, CU_TENSOR_MAP_INTERLEAVE_NONE, sw,
       CU_TENSOR_MAP_L2_PROMOTION_L2_128B, CU_TENSOR_MAP_FLOAT_OOB_FILL_NONE);
}
template <typename... Args>
static void launch_pdl(void (*kern)(Args...), int grid, int block, int smem, Args... args) {
    cudaLaunchConfig_t cfg = {};
    cfg.gridDim = dim3(grid); cfg.blockDim = dim3(block); cfg.dynamicSmemBytes = smem; cfg.stream = cudaStreamPerThread;
    cudaLaunchAttribute at[1];
    at[0].id = cudaLaunchAttributeProgrammaticStreamSerialization; at[0].val.programmaticStreamSerializationAllowed = 1;
    cfg.attrs = at; cfg.numAttrs = 1;
    cudaLaunchKernelEx(&cfg, kern, args...);
}
static void launch_stage(int k, void* const* d_in, void* d_out) {
    const Par par = {k > 1 ? nullptr : (const bf16*)d_in[4], (const bf16*)d_in[5], (const bf16*)d_in[6], (const bf16*)d_in[7], (const bf16*)d_in[8], (const bf16*)d_in[9], k > 1, 0, (const bf16*)d_in[0],
                     (uint4*)h_sym[4], (uint4*)h_sym[2], (uint4*)h_sym[6], (uint4*)h_sym[3], (uint4*)h_sym[0], (float*)h_sym[5], (uint4*)h_sym[1], (const bf16*)d_in[1], (const bf16*)d_in[2]};
    auto a1 = h_nsm == 132 ? a1_kernel<true> : a1_kernel<false>;
    switch (k) {
        case 1: a1<<<h_nsm, A1_THREADS, A1_SMEM, cudaStreamPerThread>>>(par, h_tmX0, h_tmR0, h_tmX1st, h_tmW, h_tab[0]); break;
        case 3: launch_pdl(conv_kernel, DM / CV_CPB, CV_THREADS, CV_SMEM, 0, (const uint4*)h_sym[7], (const float4*)h_sym[4], (const bf16*)h_sym[8], (bf16*)h_sym[9], (const uint4*)h_sym[0], h_tmOut); break;
        case 5: launch_pdl(a1, h_nsm, A1_THREADS, A1_SMEM, par, h_tmX1, h_tmR1, h_tmX1st, h_tmW, h_tab[1]); break;
        case 7: launch_pdl(conv_kernel, DM / CV_CPB, CV_THREADS, CV_SMEM, 1, (const uint4*)h_sym[7] + SEQ / 8, (const float4*)h_sym[4] + SEQ / 2, (const bf16*)h_sym[8], (bf16*)h_sym[10], (const uint4*)h_sym[0], h_tmOut); break;
        default: break;
    }
}
static int n_stage_kernels() { return 9; }
static const char* stage_name(int k) { const char* n[] = {"kgen", "a1", "a2", "conv", "tr", "a1", "a2", "conv", "tr"}; return n[k]; }

extern "C" void kernel_launch(void* const* d_in, const int* in_sizes, int n_in, void* d_out, int out_size) {
    (void)in_sizes; (void)n_in; (void)out_size;
    static const void *p_in = nullptr, *p_w1 = nullptr, *p_w2 = nullptr, *p_out = nullptr;
    if (p_in != d_in[0] || p_w1 != d_in[1] || p_w2 != d_in[2] || p_out != d_out) {
        cudaFuncSetAttribute(conv_kernel, cudaFuncAttributeMaxDynamicSharedMemorySize, CV_SMEM);
        cudaFuncSetAttribute(a1_kernel<true>, cudaFuncAttributeMaxDynamicSharedMemorySize, A1_SMEM);
        cudaFuncSetAttribute(a1_kernel<false>, cudaFuncAttributeMaxDynamicSharedMemorySize, A1_SMEM);
        int dev; cudaGetDevice(&dev); cudaDeviceGetAttribute(&h_nsm, cudaDevAttrMultiProcessorCount, dev);
        if (h_nsm != 132) h_nsm = 128;
        cudaGetSymbolAddress(&h_sym[0], g_tap); cudaGetSymbolAddress(&h_sym[1], g_wq); cudaGetSymbolAddress(&h_sym[2], g_wo);
        cudaGetSymbolAddress(&h_sym[3], g_halo); cudaGetSymbolAddress(&h_sym[4], g_sum); cudaGetSymbolAddress(&h_sym[5], g_csp); cudaGetSymbolAddress(&h_sym[6], g_of);
        cudaGetSymbolAddress(&h_sym[7], g_piv); cudaGetSymbolAddress(&h_sym[8], g_x1T); cudaGetSymbolAddress(&h_sym[9], g_xcT); cudaGetSymbolAddress(&h_sym[10], g_yT);
        for (int i = 0; i < 264; i++) {
            const int s = i % 132, h = (s - 64) >> 1;
            const int t = h_nsm != 132 ? s : s < 64 ? ((s >> 1) & 7) * 16 + (s >> 4) * 2 + (s & 1) : s < 120 ? (1 + h % 7) * 16 + 8 + (h / 7) * 2 + (s & 1) : s < 124 ? 128 : s - 116;
            const int hg = (4 * (t >> 6) + (t & 3)) & 7;
            const uint64_t wp = (uint64_t)h_sym[1] + hg * 10 * WQ_STAGE;
            h_tab[i / 132].e[s] = make_uint4((uint32_t)wp, (uint32_t)(wp >> 32), ((t >> 2) & 15) | (i / 132) << 4 | hg << 8 | 5 * (hg >> 2) << 16 | (uint32_t)t << 24, 0);
        }
        void *px1, *px2;
        cudaGetSymbolAddress(&px1, g_x1T); cudaGetSymbolAddress(&px2, g_xcT);
        make_tmap(&h_tmX0, d_in[0], 128 * 640, 64, 64, 64, CU_TENSOR_MAP_SWIZZLE_128B, 1280, 640, 0);
        make_tmap(&h_tmX1, px2, 128, 64 * XCP, 64, 64, CU_TENSOR_MAP_SWIZZLE_128B, XCP, 64, 0);
        make_tmap(&h_tmR0, d_in[0], 640, 1024, 80, 64, CU_TENSOR_MAP_SWIZZLE_NONE, 1280, 640, 1);
        make_tmap(&h_tmR1, px2, 64, 640, 64, 80, CU_TENSOR_MAP_SWIZZLE_128B, XCP, 64, 1);
        make_tmap(&h_tmX1st, px1, 2048, 640, 64, 80, CU_TENSOR_MAP_SWIZZLE_128B, XCP);
        make_tmap(&h_tmW.q, d_in[1], 16, 640, 16, 32, CU_TENSOR_MAP_SWIZZLE_32B, 1920, 16, 5);
        make_tmap(&h_tmW.o, d_in[2], 640, 640, 4, 0, CU_TENSOR_MAP_SWIZZLE_32B);
        make_tmap(&h_tmW.t, d_in[2], 640, 640, 2, 0, CU_TENSOR_MAP_SWIZZLE_32B);
        make_tmap(&h_tmOut, d_out, 640, 1024, 80, 8, CU_TENSOR_MAP_SWIZZLE_NONE, 1280, 640, 1);
        p_in = d_in[0]; p_w1 = d_in[1]; p_w2 = d_in[2]; p_out = d_out;
    }
    for (int k = 0; k < n_stage_kernels(); k++) launch_stage(k, d_in, d_out);
}
```

```cpp
#include <cuda_runtime.h>
#include <cuda_bf16.h>
#include <stdint.h>
#include <cuda.h>

typedef __nv_bfloat16 bf16;

constexpr int SEQ = 2048;
constexpr int DM = 640;
constexpr int NMODE = 192;

__device__ __forceinline__ float bf2f(bf16 v) { return __bfloat162float(v); }
__device__ __forceinline__ float rbf(float v) {
    uint32_t r;
    asm("cvt.rn.bf16x2.f32 %0, %1, %2;" : "=r"(r) : "f"(v), "f"(0.f));
    return __uint_as_float(r);
}
__device__ __forceinline__ uint32_t pack2(float lo, float hi) {
    __nv_bfloat162 t = __floats2bfloat162_rn(lo, hi);
    return *reinterpret_cast<uint32_t*>(&t);
}
__device__ __forceinline__ void pdl_sync() {
    asm volatile("griddepcontrol.wait;" ::: "memory");
    asm volatile("griddepcontrol.launch_dependents;" ::: "memory");
}
__device__ __forceinline__ float sqrt_apx(float v) { float r; asm("sqrt.approx.ftz.f32 %0, %1;" : "=f"(r) : "f"(v)); return r; }
__device__ __forceinline__ float rcp_apx(float v) { float r; asm("rcp.approx.ftz.f32 %0, %1;" : "=f"(r) : "f"(v)); return r; }
__device__ __forceinline__ uint32_t smem_u32(const void* p) { return (uint32_t)__cvta_generic_to_shared(p); }

constexpr int TAPB = 2944, TAPE = 928;
__device__ __align__(128) uint4 g_tap[DM * TAPB / 16];
#define XPAD 64
constexpr int XCP = SEQ + XPAD;
__device__ __align__(128) bf16 g_x1T[DM * XCP];
__device__ __align__(128) bf16 g_xcT[DM * XCP];
__device__ __align__(128) uint4 g_of[128 * 1280];
constexpr int WQ_STAGE = 240 * 128, WOB = 80 * 160;
__device__ __align__(128) uint4 g_wq[8 * 10 * WQ_STAGE / 16];
__device__ __align__(128) uint4 g_wo[64 * WOB / 16];
__device__ __align__(128) uint4 g_xb[128 * 240];
__device__ __align__(16) float g_csp[10 * 1920];
#define FSTR 32
__device__ __align__(128) float2 g_sum[2 * SEQ + 256 * FSTR];
__device__ __align__(16) bf16 g_piv[2 * SEQ];
__device__ __align__(128) bf16 g_yT[DM * XCP];
__device__ uint32_t g_epoch;
__device__ __align__(16) unsigned long long g_rstat[SEQ];
__device__ __align__(128) uint4 g_halo[640 * 148];
__device__ __forceinline__ unsigned long long tagw(uint32_t payload, uint32_t tag) { return ((unsigned long long)tag << 32) | payload; }
__device__ __forceinline__ ulonglong2 ld_tag2(const ulonglong2* p) {
    ulonglong2 v;
    asm volatile("ld.relaxed.gpu.global.v2.u64 {%0, %1}, [%2];" : "=l"(v.x), "=l"(v.y) : "l"(p) : "memory");
    return v;
}
__device__ __forceinline__ bool tag_ok(ulonglong2 v, uint32_t tag) { return (uint32_t)(v.x >> 32) == tag && (uint32_t)(v.y >> 32) == tag; }
__device__ __forceinline__ uint32_t ld_epoch() { uint32_t v; asm volatile("ld.relaxed.gpu.global.u32 %0, [%1];" : "=r"(v) : "l"(&g_epoch) : "memory"); return v + 1; }
constexpr int SPIN_MAX = 1 << 20;
__device__ __align__(128) uint32_t g_started[128];
__device__ __forceinline__ void sm_started(int slot) { asm volatile("red.relaxed.gpu.global.add.u32 [%0], 1;" ::"l"(g_started + slot) : "memory"); }
__device__ __forceinline__ void publish(int slot) {
    asm volatile("fence.proxy.async.global;" ::: "memory");
    asm volatile("red.release.gpu.global.add.u32 [%0], 1;" ::"l"(g_started + slot) : "memory");
}
__device__ __forceinline__ void await_all(int slot, uint32_t want) {
#pragma unroll 1
    for (int it = 0; it < SPIN_MAX; it++) {
        uint32_t v;
        asm volatile("ld.acquire.gpu.global.u32 %0, [%1];" : "=r"(v) : "l"(g_started + slot) : "memory");
        if (__all_sync(~0u, (int)(v - want) >= 0)) break;
        __nanosleep(50);
    }
    asm volatile("fence.proxy.async.global;" ::: "memory");
}
__device__ __noinline__ void sm_idle(int slot) {
    if (threadIdx.x != 288) return;
    asm volatile("fence.acq_rel.gpu;" ::: "memory");
    asm volatile("fence.proxy.async.global;" ::: "memory");
    sm_started(slot);
    const uint32_t want = ld_epoch() * gridDim.x;
    pdl_sync();
#pragma unroll 1
    for (int it = 0; it < SPIN_MAX; it++) {
        uint32_t v;
        asm volatile("ld.relaxed.gpu.global.u32 %0, [%1];" : "=r"(v) : "l"(g_started + slot) : "memory");
        if ((int)(v - want) >= 0) break;
        __nanosleep(100);
    }
}
struct TileTab { uint4 e[132]; };
__device__ __forceinline__ bool elect() {
    uint32_t p;
    asm volatile("{\n.reg .pred p;\nelect.sync _|p, 0xffffffff;\nselp.b32 %0, 1, 0, p;\n}" : "=r"(p));
    return p;
}
#define DBG_SYMS
#define TSTAMP(i)
#define TSTAMP1(i)
#define TSTAMP1T(i, t)
#define TSTAMP1X(i, t)
#define SPAN(k, i)
#define GSTAMP(arr, i)
#define TSTAMP2(i)
#define TSTAMP3(i)
#define TSTAMP4(i)
#define TSTAMPK(i, t)
#define TSTAMPC(i)
#define DBGC(i)
#define DBGV(i, v)
#define DBGCAL(i)

#define CSK(i)
#define CSK_END
#define CSA(i)
#define CSA_END
#define CST(i)
#define CST_END
#define CST_EXTRA 0
__device__ __forceinline__ void mma_bf16(float* d, uint32_t a0, uint32_t a1, uint32_t a2, uint32_t a3, uint32_t b0, uint32_t b1) {
    asm volatile("mma.sync.aligned.m16n8k16.row.col.f32.bf16.bf16.f32 {%0,%1,%2,%3}, {%4,%5,%6,%7}, {%8,%9}, {%0,%1,%2,%3};"
                 : "+f"(d[0]), "+f"(d[1]), "+f"(d[2]), "+f"(d[3]) : "r"(a0), "r"(a1), "r"(a2), "r"(a3), "r"(b0), "r"(b1));
}
__device__ __forceinline__ void mma_bf16_k8(float* d, uint32_t a0, uint32_t a1, uint32_t b0) {
    asm volatile("mma.sync.aligned.m16n8k8.row.col.f32.bf16.bf16.f32 {%0,%1,%2,%3}, {%4,%5}, {%6}, {%0,%1,%2,%3};"
                 : "+f"(d[0]), "+f"(d[1]), "+f"(d[2]), "+f"(d[3]) : "r"(a0), "r"(a1), "r"(b0));
}
__device__ __forceinline__ void ldsm_x4(uint32_t* r, uint32_t addr) {
    asm volatile("ldmatrix.sync.aligned.m8n8.x4.shared.b16 {%0,%1,%2,%3}, [%4];"
                 : "=r"(r[0]), "=r"(r[1]), "=r"(r[2]), "=r"(r[3]) : "r"(addr));
}

__device__ __forceinline__ void ldsm_x4_t(uint32_t* r, uint32_t addr) {
    asm volatile("ldmatrix.sync.aligned.m8n8.x4.trans.shared.b16 {%0,%1,%2,%3}, [%4];"
                 : "=r"(r[0]), "=r"(r[1]), "=r"(r[2]), "=r"(r[3]) : "r"(addr));
}
__device__ __forceinline__ void mbar_init(uint32_t bar, int count) { asm volatile("mbarrier.init.shared::cta.b64 [%0], %1;" ::"r"(bar), "r"(count)); }
__device__ __forceinline__ void mbar_arrive(uint32_t bar) { asm volatile("mbarrier.arrive.shared::cta.b64 _, [%0];" ::"r"(bar) : "memory"); }
__device__ __forceinline__ void mbar_wait(uint32_t bar, uint32_t parity) {
    asm volatile("{\n.reg .pred p;\nWAIT_LOOP:\n"
                 "mbarrier.try_wait.parity.shared::cta.b64 p, [%0], %1;\n"
                 "@p bra.uni WAIT_DONE;\nbra.uni WAIT_LOOP;\nWAIT_DONE:\n}" ::"r"(bar), "r"(parity) : "memory");
}

__device__ __forceinline__ void mbar_expect_tx(uint32_t bar, uint32_t bytes) {
    asm volatile("mbarrier.arrive.expect_tx.shared::cta.b64 _, [%0], %1;" ::"r"(bar), "r"(bytes) : "memory");
}
__device__ __forceinline__ void tma_load_2d(uint32_t dst, const void* tmap, int c0, int c1, uint32_t bar) {
    asm volatile("cp.async.bulk.tensor.2d.shared::cluster.global.mbarrier::complete_tx::bytes [%0], [%1, {%3, %4}], [%2];"
                 ::"r"(dst), "l"(tmap), "r"(bar), "r"(c0), "r"(c1) : "memory");
}
__device__ __forceinline__ void tma_load_3d(uint32_t dst, const void* tmap, int c0, int c1, int c2, uint32_t bar) {
    asm volatile("cp.async.bulk.tensor.3d.shared::cluster.global.mbarrier::complete_tx::bytes [%0], [%1, {%3, %4, %5}], [%2];"
                 ::"r"(dst), "l"(tmap), "r"(bar), "r"(c0), "r"(c1), "r"(c2) : "memory");
}
__device__ __forceinline__ void fence_async_smem() { asm volatile("fence.proxy.async.shared::cta;" ::: "memory"); }
__device__ __forceinline__ void bulk_load(uint32_t dst, const void* src, uint32_t bytes, uint32_t bar) {
    asm volatile("cp.async.bulk.shared::cluster.global.mbarrier::complete_tx::bytes [%0], [%1], %2, [%3];"
                 ::"r"(dst), "l"(src), "r"(bytes), "r"(bar) : "memory");
}
__device__ __forceinline__ void stsm_x4(uint32_t addr, uint32_t r0, uint32_t r1, uint32_t r2, uint32_t r3) {
    asm volatile("stmatrix.sync.aligned.m8n8.x4.shared.b16 [%0], {%1,%2,%3,%4};" ::"r"(addr), "r"(r0), "r"(r1), "r"(r2), "r"(r3) : "memory");
}
__device__ __forceinline__ void stsm_x4_t(uint32_t addr, uint32_t r0, uint32_t r1, uint32_t r2, uint32_t r3) {
    asm volatile("stmatrix.sync.aligned.m8n8.x4.trans.shared.b16 [%0], {%1,%2,%3,%4};" ::"r"(addr), "r"(r0), "r"(r1), "r"(r2), "r"(r3) : "memory");
}
__device__ __forceinline__ void prefetch_tmap(const void* tmap) { asm volatile("prefetch.tensormap [%0];" ::"l"(tmap) : "memory"); }

__device__ __forceinline__ float2 cexp_at(float wr2, float wi, float p) {
    float er;
    asm("ex2.approx.ftz.f32 %0, %1;" : "=f"(er) : "f"(wr2 * p));
    float th = wi * p;
    const float k = rintf(th * 0.15915494309189535f);
    th = fmaf(k, -6.2831854820251465f, th);
    th = fmaf(k, 1.7484555314695172e-7f, th);
    return make_float2(er * __cosf(th), er * __sinf(th));
}
__device__ __forceinline__ float2 cmul(float2 a, float2 b) {
    return make_float2(fmaf(a.x, b.x, -a.y * b.y), fmaf(a.x, b.y, a.y * b.x));
}
__device__ __forceinline__ float2 csqr(float2 a) { return make_float2(fmaf(a.x, a.x, -a.y * a.y), (a.x + a.x) * a.y); }
__device__ __forceinline__ uint32_t packh(float2 v) {
    uint32_t r;
    asm("cvt.rn.f16x2.f32 %0, %1, %2;" : "=r"(r) : "f"(v.y), "f"(v.x));
    return r;
}
__device__ __forceinline__ void mma_f16(float* d, uint32_t a0, uint32_t a1, uint32_t a2, uint32_t a3, uint32_t b0, uint32_t b1) {
    asm volatile("mma.sync.aligned.m16n8k16.row.col.f32.f16.f16.f32 {%0,%1,%2,%3}, {%4,%5,%6,%7}, {%8,%9}, {%0,%1,%2,%3};"
                 : "+f"(d[0]), "+f"(d[1]), "+f"(d[2]), "+f"(d[3]) : "r"(a0), "r"(a1), "r"(a2), "r"(a3), "r"(b0), "r"(b1));
}

struct Par { const bf16 *logA, *Aim, *Cre, *Cim, *logdt, *dsk; int layer, pad; const bf16* x; uint4 *sum, *wop, *of, *halo, *tap; float* csp; uint4* wq; const bf16 *wqkv, *wo; };
struct KgMaps { CUtensorMap q, o, t; };

__device__ __forceinline__ void bulk_prefetch(const void* p, uint32_t bytes) { asm volatile("cp.async.bulk.prefetch.L2.global [%0], %1;" ::"l"(p), "r"(bytes) : "memory"); }
__device__ __forceinline__ void bulk_store(void* dst, uint32_t src, uint32_t bytes) { asm volatile("cp.async.bulk.global.shared::cta.bulk_group [%0], [%1], %2;" ::"l"(dst), "r"(src), "r"(bytes) : "memory"); }
__device__ __forceinline__ void kgen_first(const Par& in, const KgMaps& tm, const uint32_t b0, const uint32_t wbar, const bool one) {
    const uint32_t blk = blockIdx.x, sec = (blk >= 40) + (blk >= 80), it = (blk >> 3) - 5 * sec, up = (blk >> 2) & 1, hi = blk >> 6;
    auto fetch = [&](int h) {
        if (blk < 120) asm volatile("cp.async.bulk.tensor.4d.shared::cluster.global.mbarrier::complete_tx::bytes [%0], [%1, {%3, %3, %4, %5}], [%2];"
                                    ::"r"(b0 + 10240 * h), "l"(&tm.q), "r"(wbar + 8 * h), "r"(0), "r"(sec * 40 + (blk & 7) * 5), "r"(2 * it + 10 * (up ^ h)) : "memory");
    };
    auto fetch_o = [&](int i) {
        asm volatile("cp.async.bulk.tensor.5d.shared::cluster.global.mbarrier::complete_tx::bytes [%0], [%1, {%3, %3, %4, %3, %5}], [%2];"
                     ::"r"(b0 + 20480 + i * 5120), "l"(&tm.o + i), "r"(wbar + 16), "r"(0), "r"((blk & 7) * 10 + (hi + i) * 4), "r"(((blk >> 3) & 7) * 5) : "memory");
    };
    if (one) {
#pragma unroll
        for (int i = 0; i < 3; i++) mbar_init(wbar + 8 * i, 1);
        asm volatile("fence.mbarrier_init.release.cluster;" ::: "memory");
        fetch(0);
    }
    __syncwarp();
    if (blk >> 20) __trap();
    if (one) {
        bulk_prefetch(in.wqkv + blk * 9600, 19200);
        fetch(1);
        bulk_prefetch(in.wo + blk * 3200, 6400);
        fetch_o(0);
        if (hi) fetch_o(1);
        mbar_expect_tx(wbar, 10240); mbar_expect_tx(wbar + 8, 10240); mbar_expect_tx(wbar + 16, 5120 + hi * 2560);
        bulk_prefetch(in.x + blk * 10240, 20480);
    }
}
template <typename F>
__device__ __forceinline__ void kgen_side(const Par& in, const uint32_t b0, const uint32_t wbar, F&& then) {
    const uint32_t blk = blockIdx.x, sec = (blk >= 40) + (blk >= 80), it = (blk >> 3) - 5 * sec, cg = (blk >> 3) & 7, hb = blk & 7;
    unsigned char* dst = reinterpret_cast<unsigned char*>(in.wq) + (hb * 10 + it) * WQ_STAGE + sec * 5120;
    unsigned char* dso = reinterpret_cast<unsigned char*>(in.wop) + (cg * 8 + (hb == cg ? 0 : hb + (hb < cg))) * WOB + (blk >> 6) * 5120;
    if (blk < 120) {
        mbar_wait(wbar, 0);
        CSK(2);
        bulk_store(dst, b0, 5120); bulk_store(dst + 15360, b0 + 5120, 5120);
        mbar_wait(wbar + 8, 0);
        CSK(3);
        bulk_store(dst + 5 * WQ_STAGE, b0 + 10240, 5120); bulk_store(dst + 5 * WQ_STAGE + 15360, b0 + 15360, 5120);
        asm volatile("cp.async.bulk.commit_group;" ::: "memory");
        asm volatile("cp.async.bulk.wait_group 0;" ::: "memory");
    }
    CSK(4);
    publish(32);
    CSK(5);
    if (blk < 128) {
        mbar_wait(wbar + 16, 0);
        bulk_store(dso, b0 + 20480, blk < 64 ? 5120 : 7680);
        asm volatile("cp.async.bulk.commit_group;" ::: "memory");
    }
    then();
    asm volatile("cp.async.bulk.wait_group 0;" ::: "memory");
}
__device__ __forceinline__ void kgen_sums(const Par& in, const uint32_t b0, const int h) {
    const int lane = threadIdx.x & 31, blk = blockIdx.x;
    if (blk < 120) {
        float cs[5][4] = {};
#pragma unroll
        for (int a = 0; a < 4; a++)
#pragma unroll
            for (int j = 0; j < 5; j++) {
                uint32_t w[4];
                ldsm_x4_t(w, b0 + h * 10240 + j * 1024 + ((lane >> 4) * 8 + (lane & 7)) * 32 + ((((lane >> 3) ^ (lane >> 2)) & 1) << 4) + (a >> 1) * 5120 + (a & 1) * 512);
                mma_bf16(cs[j], w[0], w[1], w[2], w[3], 0x3f803f80u, 0x3f803f80u);
            }
#pragma unroll
        for (int j = 0; j < 5; j++)
            if ((lane & 3) < 2) in.csp[(blk + 120 * h) * 80 + j * 16 + (lane >> 2) + 8 * (lane & 3)] = (lane & 3) ? cs[j][2] : cs[j][0];
    }
}
struct KgPar { uint32_t pw[4], ph[4], pdt, pdsk; };
__device__ __forceinline__ void kgen_load(const Par& in, const int w11, KgPar& k) {
    const uint32_t o = blockIdx.x * 480 + min(w11 * 48, w11 * 32 + 128), ow = o + (threadIdx.x & 31), oh = o + ow + (w11 < 8 ? 64 : 0);
    k.pdt = reinterpret_cast<const unsigned short*>(in.logdt)[ow / 96];
    k.pdsk = reinterpret_cast<const unsigned short*>(in.dsk)[ow / 96];
#pragma unroll
    for (int i = 0; i < 4; i++) {
        const bf16* p = i == 0 ? in.logA : i == 1 ? in.Aim : i == 2 ? in.Cre : in.Cim;
        k.pw[i] = reinterpret_cast<const uint32_t*>(p)[ow]; k.ph[i] = reinterpret_cast<const unsigned short*>(p)[oh];
    }
}
__device__ __forceinline__ void kgen_tables(const Par& in, uint4* tabs, const int w11, const KgPar& kp) {
    const int lane = threadIdx.x & 31, grp = min(w11 >> 1, 4), warp = w11 - 2 * grp;
    const int blk = blockIdx.x, d = blk * 5 + grp, tid = warp * 32 + lane;
    uint4* tab = tabs + grp * (2 * 256);
    const uint32_t *pw = kp.pw, *ph = kp.ph;
#pragma unroll
    for (int i = 0; i < 3; i++)
        if (i < 2 || w11 * 32 + lane < 36) asm volatile("st.global.v4.u32 [%0], {%1,%1,%1,%1};" ::"l"(in.halo + blk * 740 + w11 * 32 + lane + 352 * i), "r"(~0u));
    __syncwarp();
    if (w11 == 10) {
        if (lane < 16) in.sum[blk * 16 + lane] = make_uint4(0, 0, 0, 0);
        else if (lane < 20) reinterpret_cast<uint32_t*>(in.sum + 2048)[(blk * 4 + lane - 16) * FSTR] = 0;
    } else if (w11 > 1) asm volatile("bar.arrive 9, 352;" ::: "memory");
#pragma unroll
    for (int i = 0; i < 6; i++) tabs[w11 * 256 + 32 * i + lane] = make_uint4(0, 0, 0, 0);
    __syncwarp();
    CSK(1);
    const uint32_t tw = smem_u32(tabs) + w11 * 4096;
    const int g = lane >> 2, t = lane & 3;
    const int mt = lane >> 3, r = lane & 7;
    const uint32_t st1 = tw + mt * 1024 + r * 16, st2 = tw + (mt & 1) * 1024 + (mt >> 1) * 128 + ((r ^ (mt >> 1)) << 4), st3 = tw + 2048 + mt * 128 + ((r ^ mt) << 4);
    const uint32_t lda = tw + (mt & 1) * 1024 + r * 128 + (((mt >> 1) ^ r) << 4), ldb = tw + (mt >> 1) * 1024 + r * 128 + (((mt & 1) ^ r) << 4), ldc = tw + 2048 + r * 128 + ((mt ^ r) << 4);
    auto ldsm = [](uint32_t* v, uint32_t a) {
        asm volatile("ldmatrix.sync.aligned.m8n8.x4.shared.b16 {%0,%1,%2,%3}, [%4];" : "=r"(v[0]), "=r"(v[1]), "=r"(v[2]), "=r"(v[3]) : "r"(a) : "memory");
    };
    auto mma = [](float* c, const uint32_t* a, const uint32_t* b) {
        asm("mma.sync.aligned.m16n8k16.row.col.f32.f16.f16.f32 {%0,%1,%2,%3}, {%4,%5,%6,%7}, {%8,%9}, {%0,%1,%2,%3};"
            : "+f"(c[0]), "+f"(c[1]), "+f"(c[2]), "+f"(c[3]) : "r"(a[0]), "r"(a[1]), "r"(a[2]), "r"(a[3]), "r"(b[0]), "r"(b[1]));
    };
    asm volatile("st.shared.u32 [%0], %1;" ::"r"(tw + 3072), "r"(st1 ^ st2 ^ st3 ^ lda ^ ldb ^ ldc) : "memory");
    if (in.pad) __trap();
    const float dt = rbf(expf(__uint_as_float(kp.pdt << 16)));
    const uint32_t cm = __vmaxu2(__vmaxu2(pw[2] & 0x7fff7fffu, pw[3] & 0x7fff7fffu), __byte_perm(ph[2], ph[3], 0x5410) & 0x7fff7fffu);
    const int ex = min(max((int)(__float_as_uint(__uint_as_float(__reduce_max_sync(~0u, max(cm << 16, cm & 0xffff0000u))) * dt) >> 23), 20), 240);
    const float scale = __uint_as_float((uint32_t)(127 + 10 + 127 - ex) << 23), unscale = 2.0f * __uint_as_float((uint32_t)(ex - 10) << 23);
    float k2048 = 0.f;
    float acc[5][4] = {};
    uint32_t af[4][4] = {};
    auto rest = [&] {
        uint32_t b[4][4], c[8];
#pragma unroll
        for (int k = 0; k < 4; k++) {
            ldsm(b[k], ldb ^ (k << 5));
            if (!(k & 1)) ldsm(c + 2 * k, ldc ^ (k << 5));
        }
#pragma unroll
        for (int k = 0; k < 4; k++) { mma(acc[2], af[k], b[k]); mma(acc[3], af[k], b[k] + 2); mma(acc[4], af[k], c + 2 * k); }
    };
#pragma unroll 1
    for (uint32_t sel = 0x1076; sel < (grp < 4 ? 0x6000u : 0x4000u); sel += 0x2200) {
        rest();
        auto par = [&](int i) { return __uint_as_float(__byte_perm(pw[i], ph[i], sel)); };
        const float wr2 = -rbf(expf(par(0))) * dt * 1.4426950408889634f, wi = par(1) * dt;
        const float2 y1 = cexp_at(wr2, -wi, 1.f), z8 = cexp_at(wr2, wi, 8.f), y128 = cexp_at(wr2, -wi, 128.f);
        float2 h0 = make_float2(1.f, 0.f), h1 = csqr(csqr(csqr(z8)));
        float2 g0 = make_float2(par(2) * dt * scale, -par(3) * dt * scale), g1 = cmul(g0, y128);
        const float2 y256 = csqr(y128), y512 = csqr(y256), g2b = cmul(g0, y256), y2 = csqr(y1), y4 = csqr(y2), y1024 = csqr(y512);
        float2 g2 = g2b, g3 = cmul(g0, y512), g4 = cmul(g3, y512);
        k2048 += fmaf(g4.x, y1024.x, -g4.y * y1024.y);
#pragma unroll
        for (int e = 0; e < 8; e++) {
            stsm_x4((st1 ^ (e << 4)) + e * 128, packh(h0), packh(h1), packh(g0), packh(g1));
            if (e < 7) { h0 = e ? cmul(h0, z8) : z8; h1 = cmul(h1, z8); g0 = cmul(g0, y1); g1 = cmul(g1, y1); }
        }
        __syncwarp();
        uint32_t b[4][4], v[4], u[4];
#pragma unroll
        for (int k = 0; k < 4; k++) { ldsm(af[k], lda ^ (k << 5)); ldsm(b[k], (ldb ^ (k << 5)) + 2048); }
#pragma unroll
        for (int e = 0; e < 8; e++) {
            v[2 * (e & 1)] = packh(g2); v[2 * (e & 1) + 1] = packh((e & 1) ? cmul(g3, y4) : g3); u[e & 3] = packh(g4);
            if (e & 1) stsm_x4((st2 ^ ((e - 1) << 4)) + (e - 1) * 128, v[0], v[1], v[2], v[3]);
            if ((e & 3) == 3) stsm_x4((st3 ^ ((e - 3) << 4)) + (e - 3) * 128, u[0], u[1], u[2], u[3]);
            if (e < 7) {
                g2 = e == 3 ? cmul(g2b, y128) : cmul(g2, y2);
                if (e & 1) g3 = cmul(g3, y128);
                g4 = cmul(g4, y128);
            }
            mma(acc[e & 1], af[e >> 1], b[e >> 1] + 2 * (e & 1));
        }
        __syncwarp();
        if (sel == 0x1076) CSK(3);
    }
    rest();
#pragma unroll
    for (int e = 0; e < 5; e++) k2048 += __shfl_xor_sync(~0u, k2048, 1 << e);
    {
        float* Pp = reinterpret_cast<float*>(tab + warp * 256);
        auto sw = [](int i) { return i ^ ((i >> 2) & 24); };
#pragma unroll
        for (int h = 0; h < 2; h++) {
            const int b = g + 8 * h;
            *reinterpret_cast<float2*>(Pp + sw(8 * b + 2 * t)) = make_float2(acc[0][2 * h] * unscale, acc[0][2 * h + 1] * unscale);
            *reinterpret_cast<float2*>(Pp + 128 + sw(8 * b + 2 * t)) = make_float2(acc[1][2 * h] * unscale, acc[1][2 * h + 1] * unscale);
            *reinterpret_cast<float2*>(Pp + 256 + sw(4 * b + 2 * (t & 1) + 64 * (t >> 1))) = make_float2(acc[2][2 * h] * unscale, acc[2][2 * h + 1] * unscale);
            *reinterpret_cast<float2*>(Pp + 384 + sw(2 * b + 32 * t)) = make_float2(acc[3][2 * h] * unscale, acc[3][2 * h + 1] * unscale);
            Pp[512 + sw(b + 32 * t)] = acc[4][2 * h] * unscale;
            Pp[512 + sw(b + 32 * t + 16)] = acc[4][2 * h + 1] * unscale;
        }
        if (lane == 0) Pp[640] = k2048 * unscale;
    }
    CSK(4);
    asm volatile("bar.sync %0, %1;" ::"r"(grp + 4), "r"(grp < 4 ? 64 : 96) : "memory");
    if (warp == 2) return;
    const float* Kp = reinterpret_cast<const float*>(tab);
    auto ksum = [&](int i) -> float { return rbf(Kp[i] + Kp[1024 + i] + (grp < 4 ? 0.f : Kp[2048 + i])); };
    auto ksum2 = [&](int q) -> float2 {
        q ^= (q >> 2) & 12;
        const float2 a = reinterpret_cast<const float2*>(Kp)[q], b = reinterpret_cast<const float2*>(Kp)[512 + q];
        const float2 c = grp < 4 ? make_float2(0.f, 0.f) : reinterpret_cast<const float2*>(Kp)[1024 + q];
        return make_float2(a.x + b.x + c.x, a.y + b.y + c.y);
    };
    {
        uint2* W2 = reinterpret_cast<uint2*>(in.tap + d * (TAPB / 16)) + 8;
        uint2* E4 = W2 + (TAPE - 64) / 8;
        float2 v = ksum2(64 * warp + lane), z = ksum2(64 * warp + 32 + lane), y = ksum2(128 + tid);
        const int q = (96 + tid) ^ (((96 + tid) >> 2) & 6);
        const float4 ua = reinterpret_cast<const float4*>(Kp)[q], uc = reinterpret_cast<const float4*>(Kp)[256 + q], ud = grp < 4 ? make_float4(0.f, 0.f, 0.f, 0.f) : reinterpret_cast<const float4*>(Kp)[512 + q];
        const float4 ub = make_float4(uc.x + ud.x, uc.y + ud.y, uc.z + ud.z, uc.w + ud.w);
        const float s1 = ksum(tid == 31 ? 336 : lane ? 384 : 103), s2 = ksum(tid == 31 ? 512 : tid ? 640 : 231);
        if (tid == 0) v.x += __uint_as_float(kp.pdsk << 16);
        if (tid == 63) y.y -= s1;
        const uint32_t lo = pack2(v.x, v.y), hi = pack2(z.x, z.y), tp = pack2(y.x, y.y);
        uint32_t nl = __shfl_sync(~0u, lo, lane - 1), nh = __shfl_sync(~0u, lane == 31 ? lo : hi, lane - 1), nt = __shfl_sync(~0u, tp, lane + 1);
        if (lane == 0) nl = warp ? __float_as_uint(s1) : 0u;
        if (lane == 31) nt = warp ? 0u : __float_as_uint(s1) >> 16;
        W2[64 * warp + lane] = make_uint2(__byte_perm(lo, nl, 0x7610), __byte_perm(lo, 0, 0x1032));
        W2[64 * warp + lane + 32] = make_uint2(__byte_perm(hi, nh, 0x7610), __byte_perm(hi, 0, 0x1032));
        reinterpret_cast<uint4*>(W2)[64 + tid] = make_uint4(__byte_perm(tp, __float_as_uint(s2), tid ? 0x1010 : 0x7610), __byte_perm(tp, 0, 0x1010), __byte_perm(tp, 0, 0x1032), __byte_perm(nt, tp, 0x7610));
        E4[(tid < 32 ? 159 : 209 - 32) + tid] = make_uint2(pack2(ua.x + ub.x, ua.y + ub.y), pack2(ua.z + ub.z, ua.w + ub.w - (tid == 31 ? s2 : 0.f)));
        if (tid == 63) E4[241] = make_uint2(__float_as_uint(s2) >> 16, 0u);
    }
    CSK(5);
    SPAN(0, 3);
}

#define CV_SLEEP 40
#define CV_LD "ld.relaxed.gpu.global"
#define CV_NL 1
#define CV_D2 3
#define CV_PDH 12
#define CV_PDF 4
#define CV_HAND 7
constexpr int CV_CPB = 5;
constexpr int CV_THREADS = 512;
constexpr int UPADF = 128;
constexpr int ULEN = UPADF + SEQ;
constexpr int XLEN = XCP;
constexpr int BX_5 = 0, BX_3 = 3264, BX_9 = 6528, BX_7 = 8960, BX_LEN = 11392;
constexpr int CV_SM_U = 0;
constexpr int CV_SM_T = CV_CPB * ULEN * 2;
constexpr int CV_SM_B = CV_SM_T + CV_CPB * TAPB;
constexpr int CV_SM_X = CV_SM_B + CV_CPB * BX_LEN;
constexpr int CV_SM_Y = (CV_SM_X + CV_CPB * XLEN * 2 + 127) & ~127;
constexpr int CV_SM_CNT = CV_SM_Y + CV_CPB * 8192;
constexpr int CV_SM_O = CV_SM_CNT + 128;
constexpr int CV_SMEM = CV_SM_O + 20480 + CST_EXTRA;
static_assert(ULEN % 128 == 0 && CV_SM_B % 128 == 0 && CV_SM_CNT % 128 == 0, "layout");

__device__ __forceinline__ uint32_t sub2(uint32_t x, uint32_t m) {
    const __nv_bfloat162 d = __hsub2(*reinterpret_cast<const __nv_bfloat162*>(&x), *reinterpret_cast<const __nv_bfloat162*>(&m));
    return *reinterpret_cast<const uint32_t*>(&d);
}
__device__ __forceinline__ uint32_t add2(uint32_t x, uint32_t y) {
    const __nv_bfloat162 d = __hadd2_rn(*reinterpret_cast<const __nv_bfloat162*>(&x), *reinterpret_cast<const __nv_bfloat162*>(&y));
    return *reinterpret_cast<const uint32_t*>(&d);
}
__device__ __forceinline__ void wgmma_fence() { asm volatile("wgmma.fence.sync.aligned;" ::: "memory"); }
__device__ __forceinline__ void wgmma_commit() { asm volatile("wgmma.commit_group.sync.aligned;" ::: "memory"); }
template <int N> __device__ __forceinline__ void wgmma_wait() { asm volatile("wgmma.wait_group.sync.aligned %0;" ::"n"(N) : "memory"); }
__device__ __forceinline__ uint64_t make_desc(uint32_t addr, uint32_t lbo, uint32_t sbo, uint32_t mode) {
    return (uint64_t)((addr & 0x3FFFF) >> 4) | ((uint64_t)(lbo >> 4) << 16) | ((uint64_t)(sbo >> 4) << 32) | ((uint64_t)mode << 62);
}
__device__ __forceinline__ void wgmma_rs128(float (&d)[64], uint2 hi, uint2 lo, uint64_t db, int acc) {
    asm volatile("{\n.reg .pred p;\nsetp.ne.b32 p, %69, 0;\nwgmma.mma_async.sync.aligned.m64n128k16.f32.bf16.bf16 {%0,%1,%2,%3,%4,%5,%6,%7,%8,%9,%10,%11,%12,%13,%14,%15,%16,%17,%18,%19,%20,%21,%22,%23,%24,%25,%26,%27,%28,%29,%30,%31,%32,%33,%34,%35,%36,%37,%38,%39,%40,%41,%42,%43,%44,%45,%46,%47,%48,%49,%50,%51,%52,%53,%54,%55,%56,%57,%58,%59,%60,%61,%62,%63}, {%64,%65,%66,%67}, %68, p, 1, 1, 0;\n}"
                 : "+f"(d[0]), "+f"(d[1]), "+f"(d[2]), "+f"(d[3]), "+f"(d[4]), "+f"(d[5]), "+f"(d[6]), "+f"(d[7]), "+f"(d[8]), "+f"(d[9]), "+f"(d[10]), "+f"(d[11]), "+f"(d[12]), "+f"(d[13]), "+f"(d[14]), "+f"(d[15]), "+f"(d[16]), "+f"(d[17]), "+f"(d[18]), "+f"(d[19]), "+f"(d[20]), "+f"(d[21]), "+f"(d[22]), "+f"(d[23]), "+f"(d[24]), "+f"(d[25]), "+f"(d[26]), "+f"(d[27]), "+f"(d[28]), "+f"(d[29]), "+f"(d[30]), "+f"(d[31]), "+f"(d[32]), "+f"(d[33]), "+f"(d[34]), "+f"(d[35]), "+f"(d[36]), "+f"(d[37]), "+f"(d[38]), "+f"(d[39]), "+f"(d[40]), "+f"(d[41]), "+f"(d[42]), "+f"(d[43]), "+f"(d[44]), "+f"(d[45]), "+f"(d[46]), "+f"(d[47]), "+f"(d[48]), "+f"(d[49]), "+f"(d[50]), "+f"(d[51]), "+f"(d[52]), "+f"(d[53]), "+f"(d[54]), "+f"(d[55]), "+f"(d[56]), "+f"(d[57]), "+f"(d[58]), "+f"(d[59]), "+f"(d[60]), "+f"(d[61]), "+f"(d[62]), "+f"(d[63])
                 : "r"(hi.x), "r"(hi.y), "r"(lo.x), "r"(lo.y), "l"(db), "r"(acc));
}
template <int V> struct Int { __device__ constexpr operator int() const { return V; } };
__device__ __forceinline__ void sts4(uint32_t a, const uint32_t* v) { asm volatile("st.shared.v4.u32 [%0], {%1,%2,%3,%4};" ::"r"(a), "r"(v[0]), "r"(v[1]), "r"(v[2]), "r"(v[3]) : "memory"); }
__device__ __forceinline__ uint32_t lds1(uint32_t a) { uint32_t v; asm volatile("ld.shared.u32 %0, [%1];" : "=r"(v) : "r"(a) : "memory"); return v; }
__device__ __forceinline__ uint32_t lds1v(uint32_t a) { uint32_t v; asm volatile("ld.volatile.shared.u32 %0, [%1];" : "=r"(v) : "r"(a) : "memory"); return v; }
__device__ __forceinline__ uint4 lds4(uint32_t a) { uint4 v; asm volatile("ld.shared.v4.u32 {%0,%1,%2,%3}, [%4];" : "=r"(v.x), "=r"(v.y), "=r"(v.z), "=r"(v.w) : "r"(a) : "memory"); return v; }
__device__ __forceinline__ uint4 ldx(uint32_t a) {
    uint4 v;
    asm volatile("ld.shared.v2.u32 {%0,%1}, [%4];\nld.shared.v2.u32 {%2,%3}, [%4+128];" : "=r"(v.x), "=r"(v.y), "=r"(v.z), "=r"(v.w) : "r"(a) : "memory");
    return v;
}
__device__ __forceinline__ void cv_store(unsigned char* p, uint4 x, uint4 y) {
    asm volatile("st.relaxed.gpu.global.v2.u32 [%0], {%1,%2};" ::"l"(p), "r"(add2(x.x, __byte_perm(y.x, y.y, 0x5410))), "r"(add2(x.y, __byte_perm(y.z, y.w, 0x5410))) : "memory");
    asm volatile("st.relaxed.gpu.global.v2.u32 [%0], {%1,%2};" ::"l"(p + 128), "r"(add2(x.z, __byte_perm(y.x, y.y, 0x7632))), "r"(add2(x.w, __byte_perm(y.z, y.w, 0x7632))) : "memory");
}
__device__ __forceinline__ int usw(int ch) { return ch ^ ((ch >> 3) & 1); }
__global__ void __launch_bounds__(CV_THREADS, 1) conv_kernel(int layer, const uint4* __restrict__ piv, const float4* __restrict__ sum, const bf16* __restrict__ x1T,
                                                             bf16* __restrict__ dst, const uint4* __restrict__ tap, const __grid_constant__ CUtensorMap tmOut) {
    extern __shared__ __align__(1024) unsigned char sm[];
    SPAN(3 + 4 * layer, 0);
    bf16* Us = reinterpret_cast<bf16*>(sm + CV_SM_U);
    bf16* Xs = reinterpret_cast<bf16*>(sm + CV_SM_X);
#define CV_IDX int tid; asm volatile("mov.u32 %0, %tid.x;" : "=r"(tid)); const int lane = tid & 31, warp = __shfl_sync(~0u, tid >> 5, 0);
    const int d0 = blockIdx.x * CV_CPB, tile = blockIdx.x; (void)tile;
    const uint32_t cnt = smem_u32(sm + CV_SM_CNT);
    struct Lc { uint32_t a4, a8, uc, ud, y, e4, en, sp, ss; int go; };
    auto lane_consts = [&](int lane, int c) {
        const int mat = lane >> 3, r = lane & 7, g = lane >> 2, ti = lane & 3, e = g - 2 * ti;
        const int j2 = 13 + (r ^ 1) + 8 * (mat >> 1), j3 = j2 + 2, i0 = 8 * (mat & 1);
        const uint32_t sb = smem_u32(sm), oc = sb + usw(16 * (mat >> 1) + 2 * r + (mat & 1)) * 16;
        const Lc l = {sb + CV_SM_B + c * BX_LEN + ((j2 & 1) ? BX_3 + (4 * j2 + i0 + 84) * 2 : BX_5 + (4 * j2 + i0 + 80) * 2),
                      sb + CV_SM_B + c * BX_LEN + ((j3 & 1) ? BX_7 : BX_9) + (8 * j3 + i0 + 136) * 2,
                      oc + CV_SM_U + (c * ULEN + UPADF) * 2, sb + CV_SM_U + (c * ULEN + UPADF) * 2 + usw(16 * mat + 2 * r + 2) * 16, oc + CV_SM_Y + c * 8192,
                      sb + CV_SM_T + c * TAPB + TAPE + (307 + 2 * g - ti) * 4, sb + CV_SM_T + c * TAPB + (528 + e) * 4,
                      e == -5 ? 0x4410u : e == -4 ? 0x1044u : 0x4444u, e == 3 ? 0x4410u : e == 4 ? 0x1044u : 0x4444u,
                      c * XCP * 2 + (lane >> 4) * 256 + (lane & 15) * 8};
        asm volatile("st.shared.u32 [%0], %1;" ::"r"(sb + CV_SM_CNT + 120), "r"(l.y ^ l.a4 ^ l.a8 ^ l.uc ^ l.ud ^ l.e4 ^ l.en ^ l.sp ^ l.ss ^ l.go) : "memory");
        return l;
    };
    unsigned char* const dq = reinterpret_cast<unsigned char*>(dst + (size_t)d0 * XCP);
    auto far = [&](auto T0_, const auto& seq, const Lc& lc, int c, int lane, const uint2 (&f)[20], uint32_t kk) {
        constexpr int T0 = T0_, T1 = T0 + 6, TC = T0 > 7 ? T0 : 7, NS = sizeof(seq) / sizeof(seq[0]), PD = T0 > 7 ? CV_PDH : CV_PDF;
        uint32_t bq[28], yw[4], yz[4], P, S;
        uint4 xv, yv;
        asm("prmt.b32 %0, %1, 0, %2;" : "=r"(P) : "r"(kk), "r"(lc.sp));
        asm("prmt.b32 %0, %1, 0, %2;" : "=r"(S) : "r"(kk), "r"(lc.ss));
#pragma unroll
        for (int k = 0; 2 * k < T1 - TC + 4; k++) ldsm_x4(bq + 4 * k, lc.uc + (TC - 8) * 256 + 512 * k);
#pragma unroll
        for (int k = 0; 4 * k < T1 - TC; k++) ldsm_x4(bq + 20 + 4 * k, lc.ud + (TC - 8) * 256 + 1024 * k);
        CST(3);
        mbar_wait(cnt + 8 * c, 0);
        mbar_wait(cnt + 40, 0);
        CST(4);
        float acc[6][4] = {};
        uint32_t a[PD + 1][4];
#pragma unroll
        for (int i = -PD; i < NS + 3; i++) {
            if (i + PD < NS) ldsm_x4_t(a[(i + PD) % (PD + 1)], seq[i + PD] < 32 ? lc.a4 + (seq[i + PD] - 2) * 128 : lc.a8 + (seq[i + PD] - 34) * 256);
            if (i < 0) continue;
#pragma unroll
            for (int T = T0; T < T1; T++) {
                if (i >= NS) break;
                const int ee = seq[i] < 32 ? 2 * T - 6 - seq[i] : T + 35 - seq[i];
                if (i == 0 && T >= TC) mma_bf16(acc[T - T0], P, 0u, S, P, bq[2 * (T - TC)], bq[2 * (T - TC) + 1]);
                if (i == 1 && T >= TC) mma_bf16_k8(acc[T - T0], 0u, S, bq[20 + T - TC]);
                if (i == (T >= TC ? 2 : 0)) mma_bf16(acc[T - T0], f[19].x, 0u, f[19].y, f[19].x, bq[2 * (T - TC + 4)], bq[2 * (T - TC + 4) + 1]);
                if (seq[i] < 32 ? ee >= 0 && ee <= 9 : ee >= 10) mma_bf16(acc[T - T0], a[i % (PD + 1)][0], a[i % (PD + 1)][1], a[i % (PD + 1)][2], a[i % (PD + 1)][3], f[ee].x, f[ee].y);
            }
#pragma unroll
            for (int k = 0; k < 3; k++) {
                const int o = 256 * T0 + 512 * k;
                auto at = [&](int d) { return i - d >= 0 && i - d < NS && seq[i - d < 0 ? 0 : i - d < NS ? i - d : 0] == 2 * T0 + 4 * k - 4; };
                if (at(CV_D2)) {
                    cv_store(dq + lc.go + o, xv, yv);
                    if (layer > 19 - 2 * k) __trap();
                }
                if (at(-2)) { ldsm_x4_t(yw, lc.y + o); ldsm_x4_t(yz, lc.y + 3584 + o); }
                if (at(1)) {
#pragma unroll
                    for (int q = 0; q < 4; q++) yw[q] = add2(add2(yw[q], yz[q]), pack2(acc[2 * k + (q >> 1)][2 * (q & 1)], acc[2 * k + (q >> 1)][2 * (q & 1) + 1]));
                    stsm_x4_t(lc.y + o, yw[0], yw[1], yw[2], yw[3]);
                    xv = ldx(smem_u32(Xs) + lc.go + o);
                    __syncwarp();
                    yv = lds4(smem_u32(sm + CV_SM_Y) + c * 8192 + o + usw(lane) * 16);
                    if (layer > 20 - 2 * k) __trap();
                    if (k == 2) CST(6);
                }
            }
        }
    };
    TSTAMP1X(9, 256);
    if (threadIdx.x >= 256) {
        if (threadIdx.x < 288 && elect()) {
            mbar_init(cnt + 48, 1);
            asm volatile("fence.mbarrier_init.release.cluster;" ::: "memory");
            bulk_load(smem_u32(sm + CV_SM_T), tap + d0 * (TAPB / 16), CV_CPB * TAPB, cnt + 48);
            mbar_expect_tx(cnt + 48, CV_CPB * TAPB);
        }
        CV_IDX
        const int wgu = (warp >> 2) & 1, g = lane >> 2, ti = lane & 3;
        CST(1);
        if (warp > 8 && elect()) {
            if (warp < 15) mbar_init(cnt + 8 * (warp - 9), warp == 14 ? 8 : 4);
            else if (layer) prefetch_tmap(&tmOut);
        }
        if (warp < 13 && lane < 17 - (warp == 12)) {
            const int off = warp == 12 ? CV_SM_U : CV_SM_B + (warp == 11 ? BX_7 : (warp - 8) * BX_3), str = warp == 12 ? ULEN * 2 : BX_LEN;
#pragma unroll
            for (int c = 0; c < CV_CPB; c++) *reinterpret_cast<uint4*>(sm + off + c * str + 16 * lane) = make_uint4(0, 0, 0, 0);
        }
        fence_async_smem();
        asm volatile("bar.arrive 3, 512;" ::: "memory");
        asm volatile("bar.sync 1, 256;" ::: "memory");
        TSTAMP1X(10, 256);
        asm volatile("setmaxnreg.inc.sync.aligned.u32 168;");
        const uint32_t Tc = smem_u32(sm + CV_SM_T) + (16 + 128 * (warp & 2) + 8 * (warp & 1) + g - 2 * ti) * 4;
        uint2 fa[8][2], fn[8][2];
        auto near_taps = [&](uint2 (&f)[8][2], int c) {
#pragma unroll
            for (int m = 0; m < 16; m++) f[m >> 1][m & 1] = make_uint2(lds1v(Tc + c * TAPB + 64 * (m >> 1) - 32 * (m & 1)), lds1v(Tc + c * TAPB + 64 * (m >> 1) - 32 * (m & 1) + 512));
        };
        CST(6);
        mbar_wait(cnt + 48, 0);
        TSTAMP1X(11, 256); CST(5);
        near_taps(fa, 3 * wgu);
        near_taps(fn, 2 - wgu);
        const int hc = wgu ? warp & 3 : 4;
        const Lc lc = lane_consts(lane, hc);
        TSTAMP1X(12, 256); CST(0);
        uint32_t ya = smem_u32(sm + CV_SM_Y) + wgu * 8192 + (warp & 2) * 2048 + usw(2 * lane + (warp & 1)) * 16;
        uint64_t db = make_desc(smem_u32(Us + wgu * ULEN + UPADF), 16, 256, 3);
        if (wgu) { asm volatile("bar.sync 6, 384;" ::: "memory"); fence_async_smem(); }
        int c = wgu;
        auto chain = [&](const uint2 (&f)[8][2], auto&& meanwhile) {
            float acc[64];
            asm volatile("bar.sync %0, %1;" ::"r"(c ? 4 + wgu : 2), "r"(c ? 256 : 384) : "memory");
            TSTAMPC(1 + 3 * c);
            if (c < 2) CST(7);
            if (c == 0) fence_async_smem();
            wgmma_fence();
#pragma unroll
            for (int m = 0; m < 8; m++) {
                wgmma_rs128(acc, f[m][0], f[m][1], db - (uint64_t)(2 * m), m);
                if (m == CV_HAND && c < 4) asm volatile("bar.arrive %0, 256;" ::"r"(5 - wgu) : "memory");
            }
            wgmma_commit();
            asm volatile("griddepcontrol.launch_dependents;" ::: "memory");
            TSTAMPC(2 + 3 * c); CST(13 + (c >> 1));
            meanwhile();
            wgmma_wait<0>();
            TSTAMPC(3 + 3 * c); CST(10 + (c >> 1));
            uint32_t w[16];
#pragma unroll
            for (int j = 0; j < 16; j++) w[j] = j ? pack2(acc[4 * j] + acc[4 * j - 2], acc[4 * j + 1] + acc[4 * j - 1]) : pack2(acc[0], acc[1]);
#pragma unroll
            for (int j = 0; j < 16; j += 4) stsm_x4_t(ya + 256 * j, w[j], w[j + 1], w[j + 2], w[j + 3]);
            __syncwarp();
            if (lane == 0) mbar_arrive(cnt + 8 * c);
            c += 2; ya += 16384; db += ULEN / 4;
        };
        const uint32_t e4 = lc.e4, e8 = e4 + 428 - 4 * g;
        uint2 fl[4];
        uint32_t kk;
#pragma unroll 1
        for (;;) {
            if (c != 1) chain(fa, [&] {
                if (c == 3 || warp + c == 12) {
#pragma unroll
                    for (int k = 0; k < 19; k++) (k < 16 ? fn[(k >> 1) & 7][k & 1] : fl[k & 3]) = make_uint2(lds1(k < 10 ? e4 + 32 * k + 16 : e8 + 32 * k - 304), lds1(k < 10 ? e4 + 32 * k : e8 + 32 * k - 320));
                    fl[3] = make_uint2(lds1(lc.en), lds1(lc.en - 32));
                    kk = lds1(smem_u32(sm + CV_SM_T) + TAPB * hc + TAPE + 1672);
                }
            });
            if (c > 4) break;
            if (c == 2) { asm volatile("bar.sync 7, 384;" ::: "memory"); fence_async_smem(); }
            chain(fn, [&] { if (c == 2) near_taps(fa, 4); });
        }
        TSTAMP1X(6, 256); CST(2);
        if (wgu || warp == 8) {
            constexpr int seq[29] = {5, 6, 32, 7, 33, 8, 34, 9, 35, 10, 36, 11, 12, 13, 14, 15, 16, 17, 37, 18, 38, 19, 20, 21, 39, 22, 40, 23, 24};
            uint2 f[20];
#pragma unroll
            for (int k = 0; k < 20; k++) f[k] = k < 16 ? fn[(k >> 1) & 7][k & 1] : fl[k & 3];
            far(Int<10>(), seq, lc, hc, lane, f, kk);
        }
    } else {
        asm volatile("setmaxnreg.dec.sync.aligned.u32 88;");
        CV_IDX
        CST(5);
        const uint4* ppv = piv + tid;
        const float4* psv = sum + tid;
        const uint2* pxv = reinterpret_cast<const uint2*>(x1T + (size_t)d0 * XCP) + (tid >> 4) * 32 + (tid & 15);
        asm volatile("st.shared.u64 [%0], %1;" ::"r"(smem_u32(sm + CV_SM_O) + tid * 16), "l"((uint64_t)ppv ^ (uint64_t)psv ^ (uint64_t)pxv) : "memory");
        const int tc = (0x04302100 >> (4 * warp)) & 7;
        const Lc lc = lane_consts(lane, tc);
        pdl_sync();
        SPAN(3 + 4 * layer, 1);
        TSTAMP(0); CST(0);
        if (tid == 0) TSTAMPC(0);
        if (threadIdx.x == 0) { GSTAMP(g_tim, 15); }
        float4 sv[4];
        uint4 pv;
#pragma unroll
        for (int k = 0; k < 4; k++)
            asm volatile(CV_LD ".v4.f32 {%0,%1,%2,%3}, [%4];" : "=f"(sv[k].x), "=f"(sv[k].y), "=f"(sv[k].z), "=f"(sv[k].w) : "l"(psv + 256 * k) : "memory");
        asm volatile(CV_LD ".v4.u32 {%0,%1,%2,%3}, [%4];" : "=r"(pv.x), "=r"(pv.y), "=r"(pv.z), "=r"(pv.w) : "l"(ppv) : "memory");
        uint2 xe[CV_CPB], xo[CV_CPB];
#pragma unroll
        for (int c = 0; c < CV_NL; c++) {
            asm volatile(CV_LD ".v2.u32 {%0,%1}, [%2];" : "=r"(xe[c].x), "=r"(xe[c].y) : "l"(pxv + c * (XCP / 4)) : "memory");
            asm volatile(CV_LD ".v2.u32 {%0,%1}, [%2];" : "=r"(xo[c].x), "=r"(xo[c].y) : "l"(pxv + c * (XCP / 4) + 16) : "memory");
        }
#define CV_XD 300
#define CV_XW 0
        if (warp == CV_XW) {
            if (elect()) {
                const uint32_t c0 = clock();
                mbar_init(cnt + 56, 1);
                asm volatile("fence.mbarrier_init.release.cluster;" ::: "memory");
                mbar_expect_tx(cnt + 56, CV_CPB * 4096);
                while (clock() - c0 < CV_XD) ;
#pragma unroll
                for (int c = CV_NL; c < CV_CPB + CV_NL; c++) bulk_load(smem_u32(Xs + (c % CV_CPB) * XLEN), x1T + (size_t)(d0 + c % CV_CPB) * XCP, 4096, cnt + 56);
            }
            __syncwarp();
            CST(15);
        }
        constexpr float idm = 1.0f / DM;
        uint32_t mw[4];
        float rs[8];
#pragma unroll
        for (int k = 0; k < 4; k++) {
            const uint32_t pw = k == 0 ? pv.x : k == 1 ? pv.y : k == 2 ? pv.z : pv.w;
            mw[k] = pack2(fmaf(sv[k].x, idm, __uint_as_float(pw << 16)), fmaf(sv[k].z, idm, __uint_as_float(pw & 0xffff0000u)));
            uint32_t vr;
            asm("cvt.rn.relu.bf16x2.f32 %0, %1, %2;" : "=r"(vr) : "f"(fmaf(sv[k].z * -idm, sv[k].z, sv[k].w) * idm), "f"(fmaf(sv[k].x * -idm, sv[k].x, sv[k].y) * idm));
            const uint32_t ve = pack2(__uint_as_float(vr << 16) + 1e-5f, __uint_as_float(vr & 0xffff0000u) + 1e-5f);
            const uint32_t sd = pack2(sqrt_apx(__uint_as_float(ve << 16)), sqrt_apx(__uint_as_float(ve & 0xffff0000u)));
            rs[2 * k] = rcp_apx(__uint_as_float(sd << 16)); rs[2 * k + 1] = rcp_apx(__uint_as_float(sd & 0xffff0000u));
        }
        if (rs[0] != 123.f) TSTAMP(13);
        const uint32_t ua = smem_u32(Us) + usw(tid + UPADF / 8) * 16;
        uint32_t uw[CV_CPB][4];
#pragma unroll
        for (int c = 0; c < CV_CPB; c++) {
            if (c == CV_NL) {
                if (warp == CV_XW) { mbar_wait(cnt + 56, 0); CST(7); }
                asm volatile("bar.sync 10, 256;" ::: "memory");
            }
            if (c == 1 || c == 2) {
#pragma unroll
                for (int k = c; k < (c == 1 ? 2 : CV_CPB); k++) {
 const uint4 v = ldx(smem_u32(Xs + k * XLEN) + (tid >> 4) * 256 + (tid & 15) * 8); xe[k] = make_uint2(v.x, v.y); xo[k] = make_uint2(v.z, v.w); }
            }
            const uint32_t e0 = sub2(xe[c].x, mw[0]), e1 = sub2(xe[c].y, mw[1]), o0 = sub2(xo[c].x, mw[2]), o1 = sub2(xo[c].y, mw[3]);
            uw[c][0] = pack2(__uint_as_float(e0 << 16) * rs[0], __uint_as_float(o0 << 16) * rs[4]); uw[c][1] = pack2(__uint_as_float(e0 & 0xffff0000u) * rs[1], __uint_as_float(o0 & 0xffff0000u) * rs[5]);
            uw[c][2] = pack2(__uint_as_float(e1 << 16) * rs[2], __uint_as_float(o1 << 16) * rs[6]); uw[c][3] = pack2(__uint_as_float(e1 & 0xffff0000u) * rs[3], __uint_as_float(o1 & 0xffff0000u) * rs[7]);
            asm volatile("st.shared.v4.u32 [%0], {%1,%2,%3,%4};" ::"r"(ua + c * ULEN * 2), "r"(uw[c][0]), "r"(uw[c][1]), "r"(uw[c][2]), "r"(uw[c][3]) : "memory");
            if (c < 2) {
                asm volatile("bar.arrive %0, 384;" ::"r"(2 + 4 * c) : "memory");
                if (layer > 29 - c) __trap();
                CST(11 + c);
            }
        }
        asm volatile("bar.arrive 7, 384;" ::: "memory");
        asm volatile("bar.sync 3, 512;" ::: "memory");
        TSTAMP(1); CST(1);
        {
            auto box = [&](auto c0, auto c1, int chunk, int cb, bool full) {
                const uint32_t ea = smem_u32(Us + cb * ULEN) + usw(chunk + UPADF / 8 + (lane ? 1 : -1)) * 16, bx = smem_u32(sm + CV_SM_B + cb * BX_LEN) + chunk * 16;
                uint32_t lo[CV_CPB][4], hi[CV_CPB][2];
#pragma unroll
                for (int c = c0; c < c1; c++) {
                    lo[c][0] = 0;
#pragma unroll
                    for (int k = 1; k < 4; k++) lo[c][k] = __shfl_up_sync(~0u, uw[c][k], 1);
#pragma unroll
                    for (int k = 0; k < 2; k++) hi[c][k] = __shfl_down_sync(~0u, uw[c][k], 1);
                }
#pragma unroll
                for (int c = c0; c < c1; c++)
                    asm volatile("{\n.reg .pred p, q;\nsetp.eq.s32 p, %7, 0;\nsetp.eq.s32 q, %7, 31;\n@p ld.shared.v4.u32 {%0,%1,%2,%3}, [%6];\n@q ld.shared.v2.u32 {%4,%5}, [%6];\n}"
                                 : "+r"(lo[c][0]), "+r"(lo[c][1]), "+r"(lo[c][2]), "+r"(lo[c][3]), "+r"(hi[c][0]), "+r"(hi[c][1]) : "r"(ea + c * ULEN * 2), "r"(lane) : "memory");
#pragma unroll
                for (int c = c0; c < c1; c++) {
                    const uint32_t e[9] = {lo[c][1], lo[c][2], lo[c][3], uw[c][0], uw[c][1], uw[c][2], uw[c][3], hi[c][0], hi[c][1]};
                    uint32_t o[8], p[8], t[7], b3[5], b5[7];
#pragma unroll
                    for (int i = 0; i < 8; i++) { o[i] = __byte_perm(e[i], e[i + 1], 0x5432); p[i] = add2(e[i], o[i]); }
#pragma unroll
                    for (int i = 0; i < 5; i++) b3[i] = add2(o[i], p[i + 1]);
                    sts4(bx + c * BX_LEN + BX_3 + 160, b3);
#pragma unroll
                    for (int i = 1; i < 7; i++) { t[i] = add2(p[i], p[i + 1]); b5[i] = add2(t[i], e[i + 2]); }
                    sts4(bx + c * BX_LEN + BX_5 + 160, b5 + 2);
                    if (full) {
#pragma unroll
                        for (int i = 1; i < 5; i++) { b3[i] = add2(b3[i], t[i + 2]); t[i] = add2(t[i], b5[i + 2]); }
                        sts4(bx + c * BX_LEN + BX_7 + 272, b3 + 1);
                        sts4(bx + c * BX_LEN + BX_9 + 272, t + 1);
                    }
                }
            };
            auto reload = [&](int c, uint32_t a) { const uint4 v = lds4(a); uw[c][0] = v.x; uw[c][1] = v.y; uw[c][2] = v.z; uw[c][3] = v.w; };
            if (warp >= 6) {
#pragma unroll
                for (int c = 0; c < 3; c++) reload(c, ua - 1024 + (c + 2) * ULEN * 2);
            }
            if (warp >= 4) {
#pragma unroll
                for (int c = 3; c < 5; c++) reload(c, ua - 2048 + c * ULEN * 2);
            }
            box(Int<0>(), Int<3>(), warp < 6 ? tid : tid - 64, warp < 6 ? 0 : 2, warp < 4);
            if (warp >= 4) box(Int<3>(), Int<5>(), tid - 128, 0, true);
            else if (tid >= 128 - CV_CPB) {
                const int c = 127 - tid;
                const uint2 v = *reinterpret_cast<const uint2*>(Us + c * ULEN + UPADF);
                const float s1 = __uint_as_float(v.x << 16), s2 = s1 + __uint_as_float(v.x & 0xffff0000u), s3 = s2 + __uint_as_float(v.y << 16), s4 = s3 + __uint_as_float(v.y & 0xffff0000u);
                unsigned char* bc = sm + CV_SM_B + c * BX_LEN;
                *reinterpret_cast<uint32_t*>(bc + BX_5 + 156) = pack2(s1, s2);
                *reinterpret_cast<uint2*>(bc + BX_7 + 264) = make_uint2(v.x << 16, pack2(s2, s3));
                *reinterpret_cast<uint2*>(bc + BX_9 + 264) = make_uint2(pack2(s1, s2), pack2(s3, s4));
            }
        }
        __syncwarp();
        if (lane == 0) mbar_arrive(cnt + 40);
        TSTAMP(2); CST(2);
        if (layer && blockIdx.x == 0 && tid == 224) g_epoch = ld_epoch();
        __syncwarp();
        if ((0x6e >> warp) & 1) {
            constexpr int seq[16] = {0, 1, 2, 3, 4, 5, 6, 32, 7, 8, 9, 33, 10, 34, 11, 12};
            uint2 f[20];
            mbar_wait(cnt, 0);
            const uint32_t e8 = lc.e4 + 428 - (lane & 28);
#pragma unroll
            for (int k = 0; k < 13; k++) f[k] = make_uint2(lds1(k < 10 ? lc.e4 + 32 * k + 16 : e8 + 32 * k - 304), lds1(k < 10 ? lc.e4 + 32 * k : e8 + 32 * k - 320));
            f[19] = make_uint2(lds1(lc.en), lds1(lc.en - 32));
            far(Int<4>(), seq, lc, tc, lane, f, lds1(smem_u32(sm + CV_SM_T) + TAPB * tc + TAPE + 1672));
        }
    }
    {
        CV_IDX
        if ((0xc91 >> warp) & 1) {
            const int c = __popc(0xc91 & ((1 << warp) - 1));
            uint4 xv[2], yv[2];
#pragma unroll
            for (int k = 0; k < 2; k++) xv[k] = ldx(smem_u32(Xs + c * XLEN) + 512 * k + (lane >> 4) * 256 + (lane & 15) * 8);
            const uint32_t u0 = lds1(smem_u32(Us + c * ULEN) + (lane == 31 ? UPADF * 2 : 0));
            mbar_wait(cnt + 8 * c, 0);
#pragma unroll
            for (int k = 0; k < 2; k++) yv[k] = lds4(smem_u32(sm + CV_SM_Y) + c * 8192 + 512 * k + usw(lane) * 16);
            const uint4 yz = lds4(smem_u32(sm + CV_SM_Y) + c * 8192 + 4096 + usw(lane) * 16);
            const float kk = __uint_as_float(lds1(smem_u32(sm + CV_SM_T) + TAPB * c + TAPE + 1272) << 16);
            yv[1].x = add2(yv[1].x, yz.x); yv[1].y = add2(yv[1].y, yz.y); yv[1].z = add2(yv[1].z, yz.z);
            yv[1].w = pack2(fmaf(kk, __uint_as_float(u0 << 16), __uint_as_float(yv[1].w << 16) + __uint_as_float(yz.w << 16)),
                            fmaf(kk, __uint_as_float(u0 << 16) + __uint_as_float(u0 & 0xffff0000u), __uint_as_float(yv[1].w & 0xffff0000u) + __uint_as_float(yz.w & 0xffff0000u)));
#pragma unroll
            for (int k = 0; k < 2; k++) cv_store(dq + c * XCP * 2 + (lane >> 4) * 256 + (lane & 15) * 8 + 512 * k, xv[k], yv[k]);
        }
        TSTAMP(4); CST(8);
        if (layer == 1) {
            const int rb = (blockIdx.x >> 3) + (warp & 8) * 2, cg = blockIdx.x & 7, ch = (tid >> 3) & 31;
            const bf16* src = dst + (size_t)(cg * 80 + ch) * XCP + rb * 64 + (tid & 7) * 8;
            uint32_t v[3][4];
            __syncthreads();
            if (warp & 8) { const uint32_t c0 = clock(); while (clock() - c0 < 300) ; }
            uint32_t todo = (warp & 4) ? 3 : 7;
#pragma unroll 1
            for (int it = 0; it < SPIN_MAX; it++) {
#pragma unroll
                for (int k = 0; k < 3; k++)
                    if (todo >> k & 1)
                        asm volatile("ld.relaxed.gpu.global.v4.u32 {%0,%1,%2,%3}, [%4];" : "=r"(v[k][0]), "=r"(v[k][1]), "=r"(v[k][2]), "=r"(v[k][3]) : "l"(src + k * (32 * XCP)) : "memory");
#pragma unroll
                for (int k = 0; k < 3; k++)
                    if ((todo >> k & 1) && v[k][0] != ~0u && v[k][1] != ~0u && v[k][2] != ~0u && v[k][3] != ~0u) {
                        *reinterpret_cast<uint4*>(sm + (32 * k + ch) * 272 + ((tid & 7) + (warp & 8)) * 16) = make_uint4(v[k][0], v[k][1], v[k][2], v[k][3]);
                        todo ^= 1u << k;
                    }
                if (!todo) break;
                __nanosleep(CV_SLEEP);
            }
            __syncwarp();
            asm volatile("bar.sync %0, 256;" ::"r"(8 + (warp >> 3)) : "memory");
            uint32_t w[12];
#pragma unroll
            for (int k = 0; k < 3; k++) ldsm_x4(&w[4 * k], smem_u32(sm) + min(32 * k + lane, 79) * 272 + warp * 16);
            const uint32_t ot = smem_u32(sm + CV_SM_O) + warp * 1280, oa = ot + (lane & 7) * 160 + (lane >> 3) * 16;
            stsm_x4_t(oa, w[0], w[1], w[2], w[3]);
            stsm_x4_t(oa + 64, w[4], w[5], w[6], w[7]);
            asm volatile("stmatrix.sync.aligned.m8n8.x2.trans.shared.b16 [%0], {%1,%2};" ::"r"(oa + 128), "r"(w[8]), "r"(w[9]) : "memory");
            fence_async_smem();
            __syncwarp();
            if (lane == 0) {
                asm volatile("cp.async.bulk.tensor.3d.global.shared::cta.bulk_group [%0, {%1, %2, %3}], [%4];" ::"l"(&tmOut), "r"(cg * 80), "r"((rb >> 1) * 64 + 8 * (warp & 7)), "r"(rb & 1), "r"(ot) : "memory");
                asm volatile("cp.async.bulk.commit_group;" ::: "memory");
                asm volatile("cp.async.bulk.wait_group.read 0;" ::: "memory");
            }
        }
    }
    TSTAMP(3); CST(9); CST_END;
    GSTAMP(g_tim, 14);
    SPAN(3 + 4 * layer, 3);
}

template <int TA, int TB>
__device__ __forceinline__ void wgmma_n240(float (&d)[120], uint64_t da, uint64_t db, int acc) {
    asm volatile("{\n.reg .pred p;\nsetp.ne.b32 p, %124, 0;\nwgmma.mma_async.sync.aligned.m64n240k16.f32.bf16.bf16 {%0,%1,%2,%3,%4,%5,%6,%7,%8,%9,%10,%11,%12,%13,%14,%15,%16,%17,%18,%19,%20,%21,%22,%23,%24,%25,%26,%27,%28,%29,%30,%31,%32,%33,%34,%35,%36,%37,%38,%39,%40,%41,%42,%43,%44,%45,%46,%47,%48,%49,%50,%51,%52,%53,%54,%55,%56,%57,%58,%59,%60,%61,%62,%63,%64,%65,%66,%67,%68,%69,%70,%71,%72,%73,%74,%75,%76,%77,%78,%79,%80,%81,%82,%83,%84,%85,%86,%87,%88,%89,%90,%91,%92,%93,%94,%95,%96,%97,%98,%99,%100,%101,%102,%103,%104,%105,%106,%107,%108,%109,%110,%111,%112,%113,%114,%115,%116,%117,%118,%119}, %120, %121, p, 1, 1, %122, %123;\n}"
                 : "+f"(d[0]), "+f"(d[1]), "+f"(d[2]), "+f"(d[3]), "+f"(d[4]), "+f"(d[5]), "+f"(d[6]), "+f"(d[7]), "+f"(d[8]), "+f"(d[9]), "+f"(d[10]), "+f"(d[11]), "+f"(d[12]), "+f"(d[13]), "+f"(d[14]), "+f"(d[15]), "+f"(d[16]), "+f"(d[17]), "+f"(d[18]), "+f"(d[19]), "+f"(d[20]), "+f"(d[21]), "+f"(d[22]), "+f"(d[23]), "+f"(d[24]), "+f"(d[25]), "+f"(d[26]), "+f"(d[27]), "+f"(d[28]), "+f"(d[29]), "+f"(d[30]), "+f"(d[31]), "+f"(d[32]), "+f"(d[33]), "+f"(d[34]), "+f"(d[35]), "+f"(d[36]), "+f"(d[37]), "+f"(d[38]), "+f"(d[39]), "+f"(d[40]), "+f"(d[41]), "+f"(d[42]), "+f"(d[43]), "+f"(d[44]), "+f"(d[45]), "+f"(d[46]), "+f"(d[47]), "+f"(d[48]), "+f"(d[49]), "+f"(d[50]), "+f"(d[51]), "+f"(d[52]), "+f"(d[53]), "+f"(d[54]), "+f"(d[55]), "+f"(d[56]), "+f"(d[57]), "+f"(d[58]), "+f"(d[59]), "+f"(d[60]), "+f"(d[61]), "+f"(d[62]), "+f"(d[63]), "+f"(d[64]), "+f"(d[65]), "+f"(d[66]), "+f"(d[67]), "+f"(d[68]), "+f"(d[69]), "+f"(d[70]), "+f"(d[71]), "+f"(d[72]), "+f"(d[73]), "+f"(d[74]), "+f"(d[75]), "+f"(d[76]), "+f"(d[77]), "+f"(d[78]), "+f"(d[79]), "+f"(d[80]), "+f"(d[81]), "+f"(d[82]), "+f"(d[83]), "+f"(d[84]), "+f"(d[85]), "+f"(d[86]), "+f"(d[87]), "+f"(d[88]), "+f"(d[89]), "+f"(d[90]), "+f"(d[91]), "+f"(d[92]), "+f"(d[93]), "+f"(d[94]), "+f"(d[95]), "+f"(d[96]), "+f"(d[97]), "+f"(d[98]), "+f"(d[99]), "+f"(d[100]), "+f"(d[101]), "+f"(d[102]), "+f"(d[103]), "+f"(d[104]), "+f"(d[105]), "+f"(d[106]), "+f"(d[107]), "+f"(d[108]), "+f"(d[109]), "+f"(d[110]), "+f"(d[111]), "+f"(d[112]), "+f"(d[113]), "+f"(d[114]), "+f"(d[115]), "+f"(d[116]), "+f"(d[117]), "+f"(d[118]), "+f"(d[119])
                 : "l"(da), "l"(db), "n"(TA), "n"(TB), "r"(acc));
}

__device__ __forceinline__ void wgmma_n80(float (&d)[40], uint64_t da, uint64_t db, int acc) {
    asm volatile("{\n.reg .pred p;\nsetp.ne.b32 p, %42, 0;\nwgmma.mma_async.sync.aligned.m64n80k16.f32.bf16.bf16 {%0,%1,%2,%3,%4,%5,%6,%7,%8,%9,%10,%11,%12,%13,%14,%15,%16,%17,%18,%19,%20,%21,%22,%23,%24,%25,%26,%27,%28,%29,%30,%31,%32,%33,%34,%35,%36,%37,%38,%39}, %40, %41, p, 1, 1, 0, 1;\n}"
                 : "+f"(d[0]), "+f"(d[1]), "+f"(d[2]), "+f"(d[3]), "+f"(d[4]), "+f"(d[5]), "+f"(d[6]), "+f"(d[7]), "+f"(d[8]), "+f"(d[9]), "+f"(d[10]), "+f"(d[11]), "+f"(d[12]), "+f"(d[13]), "+f"(d[14]), "+f"(d[15]), "+f"(d[16]), "+f"(d[17]), "+f"(d[18]), "+f"(d[19]), "+f"(d[20]), "+f"(d[21]), "+f"(d[22]), "+f"(d[23]), "+f"(d[24]), "+f"(d[25]), "+f"(d[26]), "+f"(d[27]), "+f"(d[28]), "+f"(d[29]), "+f"(d[30]), "+f"(d[31]), "+f"(d[32]), "+f"(d[33]), "+f"(d[34]), "+f"(d[35]), "+f"(d[36]), "+f"(d[37]), "+f"(d[38]), "+f"(d[39])
                 : "l"(da), "l"(db), "r"(acc));
}

constexpr int A1_THREADS = 384;
constexpr int A1_NST = 4;
#define A1_SKEW 8
constexpr int A1_STAGE = 16384 + WQ_STAGE;
constexpr int A1_KVP = 336;
constexpr int A1_SM_KV = 2 * A1_STAGE;
constexpr int A1_SM_END = A1_NST * A1_STAGE;
constexpr int A1_SM_BAR = A1_SM_END + 3072 + 3 * WOB + 64;
constexpr int A1_SM_RS = A1_SM_END + 512;
constexpr int A1_SM_W0 = A1_SM_END + 3072, A1_SM_W3 = A1_SM_END - 3 * WOB, A1_SM_A1 = 2 * WOB, A1_SM_A0 = A1_SM_A1 + 61440;
constexpr int A1_SM_XA = A1_SM_W0 + 2 * WOB, A1_SM_XB = A1_SM_XA + 2048;
constexpr int A1_SMEM = A1_SM_BAR + 512 + 7 * CST_EXTRA / 4;
static_assert(A1_SM_W3 >= A1_SM_KV + 144 * A1_KVP && A1_SM_W3 % 512 == 0 && A1_SM_A1 % 1024 == 0 && A1_SM_A0 <= A1_SM_KV && A1_SM_A0 + 61440 <= A1_SM_W3 && A1_SMEM <= 232448 && 11 * 4096 <= A1_STAGE, "layout");
__device__ __forceinline__ constexpr uint32_t wo_off(int h) { return h * WOB + (h < 3 ? A1_SM_W0 : h < 6 ? A1_SM_W3 - 3 * WOB : -6 * WOB); }
#define A1_FRED "red.relaxed.gpu.global.add.u32"
#define A1_FLD "ld.acquire.gpu.global.u32"
#define ST_SLEEP 20
#define ST_SLEEP0 300
#define WO_LATE bar_done
#define A1_P0 2
#define A1_PW (kb - 2)
#define A1_FSPIN SPIN_MAX
#define A1_FSLEEP 40
#define YT_LAYER 1
#define WOT 352
#define A1_WOAT 6

template <int L>
__device__ __forceinline__ void a1_mainloop(float (&acc)[120], uint32_t sbase, uint32_t bars, int wg, int tile) {
    constexpr int layer = L; (void)layer;
    const uint64_t da0 = L ? make_desc(sbase + wg * 8192, 8192, 1024, 1) : make_desc(sbase + wg * 8192, 16, 1024, 1), db0 = make_desc(sbase + 16384, 1024, 256, 3);
#pragma unroll 1
    for (int t = 0;; t++) {
        const int st = t % A1_NST;
        mbar_wait(bars + 8 * st, (t / A1_NST) & 1);
        if (t == A1_SKEW && wg == 0) mbar_wait(bars + 160, 0);
        TSTAMP3(1 + t);
        if (t == 0) CSA(0);
        CSK(6 + t);
        wgmma_fence();
#pragma unroll
        for (int kk = 0; kk < 4; kk++) wgmma_n240<L, 1>(acc, da0 + (uint32_t)(st * (A1_STAGE / 16) + kk * (L ? 128 : 2)), db0 + (uint32_t)(st * (A1_STAGE / 16) + (kk >> 1) * (WQ_STAGE / 32) + (kk & 1) * 32), kk ? 1 : t);
        wgmma_commit();
        if (t == 9) break;
        if (t == A1_SKEW - 1 && wg == 0) wgmma_wait<0>(); else wgmma_wait<1>();
        if (t > 0 && (threadIdx.x & 127) == 0) {
            if (t != A1_SKEW || wg) mbar_arrive(bars + 8 * (A1_NST + (t - 1) % A1_NST));
            if (t == A1_SKEW - 1 && wg == 0) mbar_arrive(bars + 8 * (A1_NST + t % A1_NST));
        }
    }
}

template <bool MAP>
__global__ void __launch_bounds__(A1_THREADS, 1) a1_kernel(const __grid_constant__ Par in, const __grid_constant__ CUtensorMap tmX, const __grid_constant__ CUtensorMap tmR,
                                                           const __grid_constant__ CUtensorMap tmX1, const __grid_constant__ KgMaps tmW, const __grid_constant__ TileTab tab) {
#define layer in.layer
    const unsigned char* const wo = reinterpret_cast<const unsigned char*>(in.wop);
    float2* const rsum = reinterpret_cast<float2*>(in.sum);
    uint4* const of = in.of;
    extern __shared__ __align__(1024) unsigned char stg[];
    const uint32_t sbase = smem_u32(stg);
    const uint32_t bars = sbase + A1_SM_BAR;
    const uint32_t bar_stat = bars + 64, bar_kv = bars + 72, bar_rd = bars + 168;
    const uint32_t bar_wo = bars + 208, bar_done = bars + 216, bar_pv = bars + 224, bar_kvf = bars + 232, bar_f2 = bars + 248, bar_e2 = bars + 384, que = bars + 448;
    const int tid = threadIdx.x;
    CSK(0);
    const int w = __shfl_sync(~0u, tid >> 5, 0), wg = w >> 2;
    uint32_t smid;
    asm volatile("mov.u32 %0, %smid;" : "=r"(smid));
    const uint4 tv = tab.e[(MAP ? smid : blockIdx.x) + (tid & (smid >> 12))];
    const bool one = elect();
    uint32_t tz;
    const unsigned char* wq;
    auto entry = [&] { tz = __shfl_sync(~0u, tv.z, 0); wq = (const unsigned char*)(((uint64_t)__shfl_sync(~0u, tv.y, 0) << 32) | __shfl_sync(~0u, tv.x, 0)); };
    auto issue_w = [&](unsigned it) { bulk_load(sbase + (it % A1_NST) * A1_STAGE + 16384, wq + it * WQ_STAGE, WQ_STAGE, bars + 8 * (it % A1_NST)); };
    auto issue_x = [&](unsigned it, int kb) {
        asm volatile("cp.async.bulk.tensor.5d.shared::cluster.global.mbarrier::complete_tx::bytes [%0], [%1, {%3, %3, %3, %4, %5}], [%2];"
                     ::"r"(sbase + (it % A1_NST) * A1_STAGE), "l"(&tmX), "r"(bars + 8 * (it % A1_NST)), "r"(0), "r"(tz & 15), "r"(kb) : "memory");
    };
    auto first_x = [&] {
        issue_x(0, (tz >> 16) & 7); issue_x(1, ((tz >> 16) & 7) + 1);
    };
    auto expect = [&] {
#pragma unroll
        for (int i = 0; i < A1_NST; i++) mbar_expect_tx(bars + 8 * i, A1_STAGE);
    };
    if (w == 8) {
        if (one) {
            prefetch_tmap(&tmX); prefetch_tmap(&tmW.q);
#pragma unroll
            for (int i = 0; i < A1_NST; i++) mbar_init(bars + 8 * i, 1);
            asm volatile("fence.mbarrier_init.release.cluster;" ::: "memory");
        }
        __syncwarp();
        asm volatile("bar.arrive 0, 384;" ::: "memory");
        if (smid >> 12) __trap();
        entry();
        if ((tz & 0x80000010u) == 16 && one) {
            issue_w(0);
            asm volatile("griddepcontrol.wait;" ::: "memory");
            first_x();
            issue_w(1);
            expect();
            asm volatile("griddepcontrol.launch_dependents;" ::: "memory");
        }
        __syncwarp();
        if (!(tz & 16) && blockIdx.x < 128) kgen_first(in, tmW, sbase + A1_SM_W0, bars - 24, one);
        __syncwarp();
    }
    if (w > 7) CSK(8);
    const bool gen = w != 8 && in.logA && blockIdx.x < 128;
    KgPar kp;
    const int w11 = w < 8 ? 2 * (w & 3) + (w >> 2) : w - 1;
    if (gen) kgen_load(in, w11, kp);
    if (w > 7) CSK(9);
    if (w == 8) {
        const int tile = tz >> 24, mb = tz & 15, hg = (tz >> 8) & 7, kb0 = (tz >> 16) & 7;
        const unsigned l1 = (tz >> 4) & 1;
        if (__builtin_expect(!l1, 0)) {
            CSK(1);
            const uint32_t ep = ld_epoch();
            if (one) kgen_side(in, sbase + A1_SM_W0, bars - 24, [&] { if (tile < 128) { first_x(); issue_x(2, kb0 + 2); expect(); } });
            __syncwarp();
            asm volatile("bar.arrive 10, 96;" ::: "memory");
            CSK(6);
            if (tile < 128) {
                await_all(32, ep * gridDim.x);
                if (one) { issue_w(0); issue_w(1); issue_w(2); }
            }
            CSK(7);
            asm volatile("bar.sync 3, 384;" ::: "memory");
            if (tile < 128 && one) {
                fence_async_smem();
                issue_x(3, kb0 + 3); issue_w(3);
                mbar_expect_tx(bars + 240, 20480);
                bulk_load(sbase + A1_SM_W0, in.x + (size_t)(mb * 128 + hg * 16) * DM, 20480, bars + 240);
            }
            __syncwarp();
            CSK(9);
        } else asm volatile("bar.sync 3, 64;" ::: "memory");
        if (tile < 128 && elect()) {
#pragma unroll 1
            for (unsigned kb = 4 - 2 * l1; kb < 10; kb++) {
                if (kb < A1_NST) mbar_wait(bars + 8 * A1_PW, 0);
                else {
                    mbar_wait(bars + 8 * (A1_NST + kb % A1_NST), ((kb / A1_NST) - 1) & 1);
                    if (l1 && kb < 9) mbar_wait(bar_rd + 8 * (kb - A1_NST), 0);
                    mbar_expect_tx(bars + 8 * (kb % A1_NST), A1_STAGE);
                }
                issue_x(kb, kb < 5 ? kb + kb0 : kb - kb0); issue_w(kb);
                CSK(6 + kb);
                if (kb == (l1 ? A1_WOAT : 9)) {
                    if (!l1) { mbar_wait(bar_stat, 0); asm volatile("fence.proxy.async.global;" ::: "memory"); }
                    mbar_expect_tx(bar_wo, 8 * WOB);
                    bulk_load(sbase + A1_SM_W0, wo + hg * 8 * WOB, 2 * WOB, bar_wo);
                }
            }
            mbar_wait(bars + 8 * (A1_NST + 3), 1);
            bulk_load(sbase + A1_SM_W3, wo + (hg * 8 + 3) * WOB, 3 * WOB, bar_wo);
        }
        CSA(4); CSA_END;
        return;
    }
    {
        if (w < 8 && one) {
#pragma unroll 1
            for (uint32_t c = (w & 4 ? w & 2 ? 0x1111112'01111111ull : 0x1111111'01111184ull : w & 2 ? 0x3122222'01111111ull : 0x1111132'02220000ull) >> (32 * (w & 1)), b = bars + 56 * w; c; c >>= 4, b += 8)
                if (c & 15) mbar_init(b, c & 15);
            asm volatile("fence.mbarrier_init.release.cluster;" ::: "memory");
        }
        __syncwarp();
        asm volatile("bar.sync 0, 384;" ::: "memory");
        if (layer) {
            if (w == 9) asm volatile("bar.arrive 3, 64;" ::: "memory");
        } else {
            if (gen) { SPAN(0, 0); SPAN(0, 1); kgen_tables(in, reinterpret_cast<uint4*>(stg + 3 * A1_STAGE), w11, kp); }
            else if (w != 11 && w11 > 1) asm volatile("bar.arrive 9, 352;" ::: "memory");
            __syncwarp();
            if (w11 < 2) {
                asm volatile("bar.sync 10, 96;" ::: "memory");
                kgen_sums(in, sbase + A1_SM_W0, w11);
                __syncwarp();
                asm volatile("bar.arrive 9, 352;" ::: "memory");
                CSK(1);
            }
            if (w == 9) asm volatile("bar.sync 3, 384;" ::: "memory"); else asm volatile("bar.arrive 3, 384;" ::: "memory");
        }
    }
    tz = __shfl_sync(~0u, tv.z, 0);
    const int tile = tz >> 24, mb = tz & 15, hg = (tz >> 8) & 7;
    float2* rst = reinterpret_cast<float2*>(stg + A1_SM_RS) + 8;
    if (wg == 2) {
        if (w == 11 && layer == 0) {
            asm volatile("bar.sync 9, 352;" ::: "memory");
            CSK(5);
            if (one) publish(64);
            __syncwarp();
            CSK(6);
        }
        if (tile >= 128) { sm_idle(layer); return; }
        if (w == 10) {
            if (one) { prefetch_tmap(&tmR); prefetch_tmap(&tmX1); }
            uint32_t ns;
            asm volatile("mov.u32 %0, %nsmid;" : "=r"(ns));
            if (MAP && ns != 132) __trap();
        }
        __syncwarp();
        if (w == 9) {
            if (layer && one) {
                mbar_expect_tx(bar_stat, 3840);
                bulk_load(sbase + A1_SM_XB, g_xb + tile * 240, 3840, bar_stat);
            }
            __syncwarp();
            uint4* pre = of + (mb * 8 + hg) * 1280 + (tid - 288);
#pragma unroll 1
            for (int k = 0; k < 5 + 5 * layer; k++) {
#pragma unroll
                for (int i = 0; i < 8; i++) asm volatile("st.global.v4.u32 [%0], {%1,%1,%1,%1};" ::"l"(pre + 32 * i), "r"(~0u) : "memory");
                pre += k < 5 ? 256 : XCP / 8;
                if (k == 4) {
                    CSA(2);
                    asm volatile("fence.acq_rel.gpu;" ::: "memory");
                    asm volatile("fence.proxy.async.global;" ::: "memory");
                    __syncwarp();
                    if (tid == 288) mbar_arrive(bar_done);
                    CSA(3);
                    pre = reinterpret_cast<uint4*>(g_yT) + tile * (5 * XCP / 8) + (tid - 288);
                }
            }
            if (layer == 0) {
                asm volatile("griddepcontrol.launch_dependents;" ::: "memory");
                await_all(64, ld_epoch() * gridDim.x);
                CSA(5);
                float4 a[2] = {};
#pragma unroll
                for (int k = 0; k < 10; k++)
#pragma unroll
                    for (int h = 0; h < 2; h++) {
                        const int c4 = min(tid - 288 + 32 * h, 59);
                        const float4 v = __ldcg(reinterpret_cast<const float4*>(g_csp + (k / 5) * 9600 + (k % 5) * 640 + hg * 80) + c4 + (c4 / 20) * 780);
                        a[h].x += v.x; a[h].y += v.y; a[h].z += v.z; a[h].w += v.w;
                    }
#pragma unroll
                for (int h = 0; h < 2; h++)
#pragma unroll
                    for (int k = 0; k < 4; k++) {
                        const float c = 0.5f * (k == 0 ? a[h].x : k == 1 ? a[h].y : k == 2 ? a[h].z : a[h].w), c1 = c - rbf(c), c2 = c1 - rbf(c1);
                        *reinterpret_cast<uint4*>(stg + A1_SM_XB + (4 * min(tid - 288 + 32 * h, 59) + k) * 16) = make_uint4(pack2(c, c1), pack2(c2, 0.f), 0u, 0u);
                    }
                fence_async_smem();
                __syncwarp();
                if (one) {
                    bulk_store(g_xb + tile * 240, sbase + A1_SM_XB, 3840);
                    asm volatile("cp.async.bulk.commit_group;" ::: "memory");
                    asm volatile("cp.async.bulk.wait_group.read 0;" ::: "memory");
                    mbar_arrive(bar_stat);
                }
                __syncwarp();
                CSA(1);
            }
            TSTAMP1T(9, 288);
        } else {
            const int j = tid - 320;
            const uint32_t tag = ld_epoch();
            if (tid == 352) sm_started(layer);
            const int ch = j & 7, kg = (j >> 3) & 3;
            const unsigned char* src = stg + (layer ? (j >> 5) * 8192 + (hg & 3) * 2048 : A1_SM_W0 + (j >> 2) * 1280);
            const int of0 = layer ? kg * 128 + ((ch ^ kg) << 4) : (j & 7) << 4, ofx = layer ? 576 : 64, ofy = layer ? 1024 : 128;
            float s[8], q[8], p0[8];
#pragma unroll
            for (int i = 0; i < 8; i++) { s[i] = 0.f; q[i] = 0.f; }
#pragma unroll 1
            for (int it = 0; it < 5; it++) {
                uint4 v[4];
                mbar_wait(layer ? bars + 8 * (it % A1_NST) : bars + 240, layer * it / A1_NST);
#pragma unroll
                for (int k = 0; k < 4; k++) v[k] = *reinterpret_cast<const uint4*>(src + (layer ? (it % A1_NST) * A1_STAGE : it * 256) + (k & 1 ? of0 ^ ofx : of0) + (k >> 1) * ofy);
                if (it == 0) {
                    const uint4 pv = *reinterpret_cast<const uint4*>(src + (layer ? ch << 4 : 0));
                    const uint32_t w[4] = {pv.x, pv.y, pv.z, pv.w};
#pragma unroll
                    for (int i = 0; i < 4; i++) { p0[2 * i] = __uint_as_float((layer ? w[i] : w[0]) << 16); p0[2 * i + 1] = __uint_as_float(layer ? w[i] & 0xffff0000u : w[0] << 16); }
                }
                asm volatile("" :: "r"(v[0].x), "r"(v[1].x), "r"(v[2].x), "r"(v[3].x), "f"(p0[0]) : "memory");
                __syncwarp();
                if ((tid & 31) == 0) mbar_arrive(bar_rd + 8 * it);
#pragma unroll
                for (int k = 0; k < 4; k++) {
                    const uint32_t w[4] = {v[k].x, v[k].y, v[k].z, v[k].w};
#pragma unroll
                    for (int i = 0; i < 4; i++) {
                        const float a = __uint_as_float(w[i] << 16) - p0[2 * i], b = __uint_as_float(w[i] & 0xffff0000u) - p0[2 * i + 1];
                        s[2 * i] += a; s[2 * i + 1] += b; q[2 * i] = fmaf(a, a, q[2 * i]); q[2 * i + 1] = fmaf(b, b, q[2 * i + 1]);
                    }
                }
            }
            float o[4];
            int row;
            if (layer == 0) {
                float s0 = ((s[0] + s[1]) + (s[2] + s[3])) + ((s[4] + s[5]) + (s[6] + s[7])), q0 = ((q[0] + q[1]) + (q[2] + q[3])) + ((q[4] + q[5]) + (q[6] + q[7]));
#pragma unroll
                for (int o = 1; o <= 2; o <<= 1) { s0 += __shfl_xor_sync(~0u, s0, o); q0 += __shfl_xor_sync(~0u, q0, o); }
                if ((j & 3) == 0) {
                    const float d = s0 * (1.0f / DM);
                    const uint32_t ms = pack2(p0[0] + d, sqrt_apx(rbf(rbf(fmaxf(fmaf(-d, d, q0 * (1.0f / DM)), 0.f)) + 1e-5f)));
                    asm volatile("st.global.cg.u64 [%0], %1;" ::"l"(g_rstat + mb * 128 + (j & 4) * 16 + hg * 8 + (j >> 3)), "l"(tagw(ms, tag)) : "memory");
                    g_piv[mb * 128 + hg * 16 + ((j >> 2) & 8) + (j & 4) + ((j >> 3) & 3)] = __ushort_as_bfloat16((unsigned short)ms);
                }
                ulonglong2 v;
#pragma unroll 1
                for (int it = 0; it < SPIN_MAX; it++) {
                    v = ld_tag2(reinterpret_cast<const ulonglong2*>(g_rstat + mb * 128) + j);
                    if (tag_ok(v, tag)) break;
                    __nanosleep(100);
                }
                o[0] = __uint_as_float((uint32_t)v.x << 16); o[1] = rcp_apx(__uint_as_float((uint32_t)v.x & 0xffff0000u));
                o[2] = __uint_as_float((uint32_t)v.y << 16); o[3] = rcp_apx(__uint_as_float((uint32_t)v.y & 0xffff0000u));
                row = 2 * j;
            } else {
#pragma unroll
                for (int i = 0; i < 4; i++) {
                    const bool up = kg & 2;
                    const float ss = __shfl_xor_sync(~0u, up ? s[i] : s[i + 4], 16), qq = __shfl_xor_sync(~0u, up ? q[i] : q[i + 4], 16);
                    s[i] = (up ? s[i + 4] : s[i]) + ss; q[i] = (up ? q[i + 4] : q[i]) + qq; p0[i] = up ? p0[i + 4] : p0[i];
                }
#pragma unroll
                for (int i = 0; i < 2; i++) {
                    const bool up = kg & 1;
                    const float ss = __shfl_xor_sync(~0u, up ? s[i] : s[i + 2], 8), qq = __shfl_xor_sync(~0u, up ? q[i] : q[i + 2], 8);
                    s[i] = (up ? s[i + 2] : s[i]) + ss; q[i] = (up ? q[i + 2] : q[i]) + qq; p0[i] = up ? p0[i + 2] : p0[i];
                }
                uint4* gp = g_halo + 86016 + mb * 512 + j;
                const float d0 = s[0] * (1.0f / 80.0f), d1 = s[1] * (1.0f / 80.0f);
                asm volatile("st.relaxed.gpu.global.v4.f32 [%0], {%1,%2,%3,%4};" ::"l"(gp + hg * 64), "f"(p0[0] + d0), "f"(fmaxf(fmaf(-d0, s[0], q[0]), 0.f)), "f"(p0[1] + d1), "f"(fmaxf(fmaf(-d1, s[1], q[1]), 0.f)) : "memory");
                __nanosleep(ST_SLEEP0);
                uint32_t pw[8][4], todo = 0xff;
#pragma unroll 1
                for (int it = 0; it < SPIN_MAX; it++) {
#pragma unroll
                    for (int k = 0; k < 8; k++)
                        if (todo >> k & 1) asm volatile("ld.relaxed.gpu.global.v4.u32 {%0,%1,%2,%3}, [%4];" : "=r"(pw[k][0]), "=r"(pw[k][1]), "=r"(pw[k][2]), "=r"(pw[k][3]) : "l"(gp + k * 64) : "memory");
#pragma unroll
                    for (int k = 0; k < 8; k++)
                        if (__all_sync(~0u, pw[k][0] != ~0u && pw[k][1] != ~0u && pw[k][2] != ~0u && pw[k][3] != ~0u)) todo &= ~(1u << k);
                    if (!todo) break;
                    __nanosleep(ST_SLEEP);
                }
#pragma unroll
                for (int r = 0; r < 2; r++) {
                    float mean = 0.f, m2 = 0.f;
#pragma unroll
                    for (int k = 0; k < 8; k++) mean += __uint_as_float(pw[k][2 * r]);
                    mean *= 0.125f;
#pragma unroll
                    for (int k = 0; k < 8; k++) {
                        const float dm = __uint_as_float(pw[k][2 * r]) - mean;
                        m2 += fmaf(80.0f * dm, dm, __uint_as_float(pw[k][2 * r + 1]));
                    }
                    o[2 * r] = rbf(mean);
                    o[2 * r + 1] = rcp_apx(rbf(sqrt_apx(rbf(rbf(m2 * (1.0f / DM)) + 1e-5f))));
                }
                row = (j >> 5) * 64 + (j & 7) * 8 + ((j >> 3) & 3) * 2;
                if (hg == 0) *reinterpret_cast<uint32_t*>(g_piv + SEQ + mb * 128 + 2 * (row & 60) + 4 * (row >> 6) + (row & 3)) = __byte_perm(__float_as_uint(o[0]), __float_as_uint(o[2]), 0x7632);
            }
#pragma unroll
            for (int r = 0; r < 2; r++)
                *reinterpret_cast<uint4*>(stg + A1_SM_XA + (row + r) * 16) = make_uint4(__byte_perm(__float_as_uint(-o[2 * r]), 0, 0x3232), __float_as_uint(-o[2 * r]) >> 16, 0u, 0u);
            *reinterpret_cast<float4*>(rst + row + (row >> 6) * 8) = make_float4(o[0], o[1], o[2], o[3]);
            fence_async_smem();
            TSTAMP1T(7, 320); CSA(1);
            if (tid == 320) DBGC(44);
            __syncwarp();
            if ((tid & 31) == 0) mbar_arrive(bar_stat);
        }
        CSA(4); CSA_END;
        if (tid == 320) DBGCAL(0);
        if (tid == WOT) {
            mbar_wait(WO_LATE, 0);
            mbar_wait(bar_done, 0);
            bulk_load(sbase, wo + (hg * 8 + 6) * WOB, 2 * WOB, bar_wo);
            bulk_load(sbase + A1_SM_W0 + 2 * WOB, wo + (hg * 8 + 2) * WOB, WOB, bar_wo);
        }
        __syncwarp();
#define FWA 11
#define FWB 10
        if (w == FWA || w == FWB) {
            const int cw = w == FWB;
            const uint32_t* fl = reinterpret_cast<const uint32_t*>(rsum + 2 * SEQ) + (((layer * 16 + mb) * 2 + cw) * 8 + (tid & 7)) * FSTR;
            const unsigned char* src = reinterpret_cast<const unsigned char*>(of) + mb * 163840 + cw * 10240 + (tid & 7) * 20480;
            const uint32_t sl = sbase + (cw ? A1_SM_A1 : A1_SM_A0);
            mbar_wait(cw ? bar_done : bar_kvf, 0);
            if ((tid & 31) == 0) {
                mbar_expect_tx(bar_f2 + 64 * cw + 64, 10240);
                tma_load_3d(sl + 51200, &tmR, layer ? 0 : hg * 80, layer ? hg * 80 : mb * 64, layer ? mb * 2 + cw : cw, bar_f2 + 64 * cw + 64);
            }
            __syncwarp();
            uint32_t pend = 0xffu & ~(1u << hg), v = 0;
            const uint32_t bo = wo_off((tid & 7) + ((tid & 7) < hg)) >> 4, lt = (1u << (tid & 31)) - 1;
#pragma unroll 1
            for (int it = 0; pend && it < 2 * SPIN_MAX; it++) {
                if (v != 4 && (pend >> (tid & 31) & 1)) asm volatile(A1_FLD " %0, [%1];" : "=r"(v) : "l"(fl) : "memory");
                uint32_t fr;
                asm volatile("{\n.reg .pred p;\nmbarrier.test_wait.parity.shared::cta.b64 p, [%1], 0;\nselp.b32 %0, 1, 0, p;\n}" : "=r"(fr) : "r"(bar_e2 + 16 * cw + (tid & 1) * 8) : "memory");
                fr = __ballot_sync(~0u, fr);
                uint32_t m = __ballot_sync(~0u, v == 4 || it >= A1_FSPIN) & pend;
                const int q = 8 - __popc(pend) + __popc(m & lt);
                m &= __ballot_sync(~0u, q < ((fr & 2) ? 8 : (fr & 1) ? 7 : 5));
                pend ^= m;
                if (m >> (tid & 31) & 1) DBGC(12 + cw * 8 + (tid & 7));
                if (!m) __nanosleep(A1_FSLEEP);
                else asm volatile("fence.proxy.async.global;" ::: "memory");
                if (m >> (tid & 31) & 1) {
                    bulk_load(q == 7 && !cw ? sbase + A1_SM_W0 : sl + (q < 6 ? q : q - 6) * 10240, src, 10240, bar_f2 + 64 * cw + 8 * q);
                    asm volatile("st.shared.u32 [%0], %1;" ::"r"(que + 32 * cw + 4 * q), "r"(bo) : "memory");
                    mbar_expect_tx(bar_f2 + 64 * cw + 8 * q, 10240);
                    DBGC(44 + cw * 8 + q);
                }
                __syncwarp();
            }
        }
    } else if (tile < 128) {
        SPAN(1 + 4 * layer, 0);
        constexpr int on = 1;
        float acc[120];
        const int lane = tid & 31, warp = w & 7, g = lane >> 2, t = lane & 3;
        if (on) {
            SPAN(1 + 4 * layer, 1);
            TSTAMP1(0);
            if (threadIdx.x == 0) { GSTAMP(g_tim1, 15); }
            TSTAMP3(0);
            if (tid == 0) TSTAMP2(0);
            TSTAMP4(0);
            if (tid == 0) DBGC(60);
            if (layer == 0) a1_mainloop<0>(acc, sbase, bars, wg, tile); else a1_mainloop<1>(acc, sbase, bars, wg, tile);
            uint32_t ok;
            asm volatile("{\n.reg .pred p;\nmbarrier.test_wait.parity.shared::cta.b64 p, [%1], 0;\nselp.b32 %0, 1, 0, p;\n}" : "=r"(ok) : "r"(bar_stat) : "memory");
            if (tid == 128 && !ok) mbar_arrive(bars + 160);
            __syncwarp();
            mbar_wait(bar_stat, 0);
            wgmma_fence();
            wgmma_n240<0, 0>(acc, make_desc(sbase + A1_SM_XA + wg * 1024, 0, 128, 0), make_desc(sbase + A1_SM_XB, 0, 128, 0), 1);
            wgmma_commit();
            if (tid == 128 && ok) mbar_arrive(bars + 160);
            mbar_wait(bars + 8 * (A1_NST + 3), 1);
        }
        const float2* rw = rst + 16 * warp + 8 * wg;
        const float rb0 = rw[g + 8].y, ra = rw[g].y * 0.22360679774997896f, rb = rb0 * 0.22360679774997896f;
        wgmma_wait<0>();
        if ((tid & 127) == 0) mbar_arrive(bar_done);
        TSTAMP1(2); CSA(1);
        TSTAMP1T(13, 224);
        if ((tid & 127) == 0) DBGC(62 - wg);
        uint32_t f[2][30];
#pragma unroll
        for (int j = 10; j < 30; j++) f[1][j] = pack2(acc[4 * j + 2], acc[4 * j + 3]);
        if ((warp & 3) == 3) {
            uint4* hout = g_halo + (((layer * 16 + mb) * 8 + hg) * 2 + wg) * 168;
#pragma unroll
            for (int j = 0; j < 20; j += 4)
                asm volatile("st.relaxed.gpu.global.v4.u32 [%0], {%1,%2,%3,%4};" ::"l"(hout + 8 * j + lane), "r"(f[1][10 + j]), "r"(f[1][11 + j]), "r"(f[1][12 + j]), "r"(f[1][13 + j]) : "memory");
            if (t == 0) asm volatile("st.relaxed.gpu.global.f32 [%0], %1;" ::"l"(reinterpret_cast<float*>(hout + 160) + g), "f"(rb0) : "memory");
        }
        TSTAMP1T(12, 224);
        const uint32_t kvw = sbase + A1_SM_KV + (16 * warp + 8 * wg) * A1_KVP;
        const uint32_t mrow = kvw + (lane & 7) * A1_KVP + (lane >> 3) * 16;
#pragma unroll
        for (int j = 0; j < 20; j += 4) stsm_x4(mrow + 16 * A1_KVP + 16 * j, f[1][10 + j], f[1][11 + j], f[1][12 + j], f[1][13 + j]);
        __syncwarp();
        if (lane == 0 && (warp & 3) != 3) mbar_arrive(bar_kv + 8 * (warp + 1));
#pragma unroll
        for (int j = 0; j < 30; j++) f[0][j] = pack2(acc[4 * j], acc[4 * j + 1]);
        stsm_x4(mrow + 8 * A1_KVP + 160, f[0][20], f[0][21], f[0][22], f[0][23]);
        stsm_x4(mrow + 8 * A1_KVP + 224, f[0][24], f[0][25], f[0][26], f[0][27]);
        asm volatile("stmatrix.sync.aligned.m8n8.x2.shared.b16 [%0], {%1,%2};" ::"r"(mrow + 8 * A1_KVP + 288), "r"(f[0][28]), "r"(f[0][29]) : "memory");
#pragma unroll
        for (int j = 0; j < 10; j++) f[1][j] = pack2(acc[4 * j + 2], acc[4 * j + 3]);
        __syncwarp();
        uint32_t vb[10][2], vp[12], kp[12];
#pragma unroll
        for (int j = 0; j < 10; j += 2) ldsm_x4_t(&vb[j][0], kvw + (8 + (lane & 15)) * A1_KVP + 160 + (lane >> 4) * 16 + 16 * j);
        const bool up0 = 2 * t > g, up1 = 2 * t + 1 > g, edge = (mb | (warp & 3)) == 0;
        float rk[4];
        auto above = [&]() {
            mbar_wait(bar_kv + 8 * warp, 0);
#pragma unroll
            for (int j = 0; j < 12; j += 4) ldsm_x4(&kp[j], mrow + 16 * j);
            rk[0] = rw[2 * t - (up0 ? 8 : 0)].y; rk[1] = rw[2 * t + 1 - (up1 ? 8 : 0)].y;
#pragma unroll
            for (int j = 0; j < 12; j += 4) ldsm_x4_t(&vp[j], mrow + 160 + 16 * j - (j == 8 ? (lane & 16) * 2 : 0));
            __syncwarp();
            if (lane == 0) mbar_arrive(bar_kvf);
        };
        auto halo = [&]() {
            if (lane == 0) mbar_arrive(bar_kvf);
            const uint4* hin = g_halo + (((layer * 16 + mb - 1) * 8 + hg) * 2 + wg) * 168;
            uint32_t hv[22] = {};
            rk[0] = rw[2 * t].y; rk[1] = rw[2 * t + 1].y;
            if (mb > 0) {
#pragma unroll 1
                for (int it = 0; it < SPIN_MAX; it++) {
#pragma unroll
                    for (int k = 0; k < 20; k += 4)
                        asm volatile("ld.relaxed.gpu.global.v4.u32 {%0,%1,%2,%3}, [%4];" : "=r"(hv[k]), "=r"(hv[k + 1]), "=r"(hv[k + 2]), "=r"(hv[k + 3]) : "l"(hin + 8 * k + lane) : "memory");
                    asm volatile("ld.relaxed.gpu.global.v2.u32 {%0,%1}, [%2];" : "=r"(hv[20]), "=r"(hv[21]) : "l"(reinterpret_cast<const uint2*>(hin + 160) + t) : "memory");
                    uint32_t m = max(hv[20], hv[21]);
#pragma unroll
                    for (int k = 0; k < 20; k += 2) m = __vimax3_u32(m, hv[k], hv[k + 1]);
                    if (!__any_sync(~0u, m == ~0u)) break;
                }
            }
            if (lane == 0) DBGC(52 - 16 * wg);
#pragma unroll
            for (int j = 0; j < 10; j++) {
                kp[j] = hv[j];
                asm volatile("movmatrix.sync.aligned.m8n8.trans.b16 %0, %1;" : "=r"(vp[j]) : "r"(hv[10 + j]));
            }
            if (up0) rk[0] = __uint_as_float(hv[20]);
            if (up1) rk[1] = __uint_as_float(hv[21]);
        };
        rk[2] = rw[2 * t + (up0 ? 0 : 8)].y; rk[3] = rw[2 * t + 1 + (up1 ? 0 : 8)].y;
        uint32_t qs[4][2];
#pragma unroll
        for (int h = 0; h < 4; h++) {
            qs[h][0] = (t >> 1) == (h & 1) ? f[0][5 * (h >> 1) + 2] : 0u; qs[h][1] = (t >> 1) == (h & 1) ? f[1][5 * (h >> 1) + 2] : 0u;
            asm volatile("" : "+r"(qs[h][0]), "+r"(qs[h][1]));
        }
#pragma unroll
        for (int j = 0; j < 10; j++) asm volatile("" : "+r"(f[0][j]), "+r"(f[1][j]), "+r"(f[0][10 + j]));
        if (warp & 3) above(); else if (wg) halo();
        TSTAMP1T(10, 64); CSA(2);
        if (warp && !wg) mbar_wait(bars + 416 + 8 * warp, 0);
        CSA(3);
        float sc[4][3][4];
#pragma unroll
        for (int h = 0; h < 4; h++) {
            const int jb = 5 * (h >> 1) + 3 * (h & 1), js = 5 * (h >> 1) + 2;
#pragma unroll
            for (int nt = 1; nt < 3; nt++) {
#pragma unroll
                for (int e = 0; e < 4; e++) sc[h][nt][e] = 0.f;
                mma_bf16(sc[h][nt], f[0][jb], f[1][jb], f[0][jb + 1], f[1][jb + 1], f[nt - 1][10 + jb], f[nt - 1][11 + jb]);
                mma_bf16_k8(sc[h][nt], qs[h][0], qs[h][1], f[nt - 1][10 + js]);
            }
        }
        if (warp == 0) halo();
        TSTAMP1(8); CSA(4);
#pragma unroll
        for (int h = 0; h < 4; h++) {
            const int jb = 5 * (h >> 1) + 3 * (h & 1), js = 5 * (h >> 1) + 2;
#pragma unroll
            for (int e = 0; e < 4; e++) sc[h][0][e] = 0.f;
            mma_bf16(sc[h][0], f[0][jb], f[1][jb], f[0][jb + 1], f[1][jb + 1], kp[jb], kp[jb + 1]);
            mma_bf16_k8(sc[h][0], qs[h][0], qs[h][1], kp[js]);
        }
        TSTAMP1T(3, 64);
        float p[4][4], sum[4][2];
        uint32_t lg[4][2], mx[4];
        const float rl[4] = {rk[0] * ra, rk[1] * ra, rk[2] * rb, rk[3] * rb};
        auto max2 = [](uint32_t a, uint32_t b) { uint32_t r; asm("max.bf16x2 %0, %1, %2;" : "=r"(r) : "r"(a), "r"(b)); return r; };
#pragma unroll
        for (int h = 0; h < 4; h++) {
            lg[h][0] = pack2((up0 ? sc[h][0][0] : sc[h][1][0]) * rl[0], (up0 ? sc[h][1][2] : sc[h][2][2]) * rl[2]);
            lg[h][1] = pack2((up1 ? sc[h][0][1] : sc[h][1][1]) * rl[1], (up1 ? sc[h][1][3] : sc[h][2][3]) * rl[3]);
            if (edge) {
                if (up0) lg[h][0] = __byte_perm(lg[h][0], 0xce6eu, 0x3254);
                if (up1) lg[h][1] = __byte_perm(lg[h][1], 0xce6eu, 0x3254);
            }
            mx[h] = max2(lg[h][0], lg[h][1]);
        }
#pragma unroll
        for (int o = 1; o <= 2; o <<= 1)
#pragma unroll
            for (int h = 0; h < 4; h++) mx[h] = max2(mx[h], __shfl_xor_sync(~0u, mx[h], o));
#pragma unroll
        for (int h = 0; h < 4; h++)
#pragma unroll
            for (int r = 0; r < 2; r++) {
                const float m = __uint_as_float(r ? mx[h] & 0xffff0000u : mx[h] << 16);
#pragma unroll
                for (int e = 0; e < 2; e++)
                    asm("ex2.approx.ftz.f32 %0, %1;" : "=f"(p[h][2 * r + e]) : "f"((__uint_as_float(r ? lg[h][e] & 0xffff0000u : lg[h][e] << 16) - m) * 1.4426950408889634f));
                sum[h][r] = p[h][2 * r] + p[h][2 * r + 1];
            }
#pragma unroll
        for (int o = 1; o <= 2; o <<= 1)
#pragma unroll
            for (int h = 0; h < 4; h++)
#pragma unroll
                for (int r = 0; r < 2; r++) sum[h][r] += __shfl_xor_sync(~0u, sum[h][r], o);
        TSTAMP1T(5, 64); CSA(5);
        const uint32_t mu = (up0 ? 0xffffu : 0u) | (up1 ? 0xffff0000u : 0u);
        uint32_t ob[10][2];
#pragma unroll
        for (int P = 0; P < 2; P++) {
            float os[2][4];
#pragma unroll
            for (int e = 0; e < 2; e++) {
                const int h = 2 * P + e;
                const float i0 = rcp_apx(sum[h][0]), i1 = rcp_apx(sum[h][1]);
                const uint32_t w0 = pack2(p[h][0] * rk[0] * i0, p[h][1] * rk[1] * i0), w1 = pack2(p[h][2] * rk[2] * i1, p[h][3] * rk[3] * i1);
#pragma unroll
                for (int dt = 0; dt < 3; dt++) {
                    const int j = 5 * P + (dt < 2 ? 3 * e + dt : 2);
                    float o[4] = {0.f, 0.f, 0.f, 0.f};
                    mma_bf16(o, w0 & ~mu, w1 & mu, 0u, w1 & ~mu, vb[j][0], vb[j][1]);
                    mma_bf16_k8(o, w0 & mu, 0u, vp[j]);
                    if (dt < 2) { ob[j][0] = pack2(o[0], o[1]); ob[j][1] = pack2(o[2], o[3]); }
                    else { os[e][0] = o[0]; os[e][1] = o[1]; os[e][2] = o[2]; os[e][3] = o[3]; }
                }
            }
#pragma unroll
            for (int k = 0; k < 4; k++) os[0][k] = t < 2 ? os[0][k] : os[1][k];
            ob[5 * P + 2][0] = pack2(os[0][0], os[0][1]); ob[5 * P + 2][1] = pack2(os[0][2], os[0][3]);
        }
        const uint32_t sl = sbase + (wg ? A1_SM_A1 : A1_SM_A0);
        const uint32_t o0 = (warp & 3) * 2048 + g * 64 + ((t ^ (g >> 1)) << 4), o1 = 8192 + (warp & 3) * 512 + g * 32 + ((t ^ ((g >> 2) << 1)) << 3);
        CSA(15);
        mbar_wait(bar_done, 0);
        if (wg == 0) mbar_wait(bar_kvf, 0);
#pragma unroll
        for (int h = 0; h < 2; h++) {
            asm volatile("st.shared.v4.u32 [%0], {%1,%2,%3,%4};" ::"r"(sl + o0 + h * 1024), "r"(ob[0][h]), "r"(ob[1][h]), "r"(ob[2][h]), "r"(ob[3][h]) : "memory");
            asm volatile("st.shared.v4.u32 [%0], {%1,%2,%3,%4};" ::"r"(sl + o0 + h * 1024 + 512), "r"(ob[4][h]), "r"(ob[5][h]), "r"(ob[6][h]), "r"(ob[7][h]) : "memory");
            asm volatile("st.shared.v2.u32 [%0], {%1,%2};" ::"r"(sl + o1 + h * 256), "r"(ob[8][h]), "r"(ob[9][h]) : "memory");
        }
        if (wg && lane == 0) mbar_arrive(bars + 384 + 8 * warp);
        fence_async_smem();
        __syncwarp();
        TSTAMP1T(4, 64); CSA(6);
        TSTAMP1(1);
        TSTAMP2(1);
        const unsigned char* ot = reinterpret_cast<const unsigned char*>(of) + mb * 163840 + wg * 10240;
        if (lane == 0) {
            asm volatile("cp.async.bulk.global.shared::cta.bulk_group [%0], [%1], 2048;" ::"l"(ot + hg * 20480 + (warp & 3) * 2048), "r"(sl + (warp & 3) * 2048) : "memory");
            asm volatile("cp.async.bulk.global.shared::cta.bulk_group [%0], [%1], 512;" ::"l"(ot + hg * 20480 + 8192 + (warp & 3) * 512), "r"(sl + 8192 + (warp & 3) * 512) : "memory");
            asm volatile("cp.async.bulk.commit_group;" ::: "memory");
            if (wg == 0) mbar_arrive(bar_pv);
            asm volatile("cp.async.bulk.wait_group 0;" ::: "memory");
            asm volatile(A1_FRED " [%0], 1;" ::"l"(reinterpret_cast<uint32_t*>(rsum + 2 * SEQ) + (((layer * 16 + mb) * 2 + wg) * 8 + hg) * FSTR) : "memory");
            DBGC(4 + warp);
        }
        TSTAMP4(11); CSA(7);
        float ac2[40];
        const uint64_t db0 = make_desc(sbase, 1024, 256, 3), db1 = make_desc(sbase + 10240, 512, 256, 3), da0 = make_desc(sl, 16, 1024, 2), da1 = make_desc(sl + 8192, 16, 256, 3);
        const uint32_t o7 = wg ? 640 : (A1_SM_W0 - A1_SM_A0) >> 4;
        const uint32_t trow = ((lane & 7) + 8 * (lane >> 4)) * 128 + (((2 * (warp & 3) + ((lane >> 3) & 1)) ^ (lane & 7)) << 4);
        uint32_t xr[10][2];
        mbar_wait(bar_f2 + 64 * wg + 64, 0);
        if (layer == 0) {
#pragma unroll
            for (int j = 0; j < 10; j += 2) ldsm_x4(&xr[j][0], sl + 51200 + (16 * (warp & 3) + (lane & 15)) * 160 + (lane >> 4) * 16 + 16 * j);
        } else {
#pragma unroll
            for (int j = 0; j < 10; j += 2) ldsm_x4_t(&xr[j][0], sl + 51200 + trow + 1024 * j);
        }
        const uint32_t ri = __shfl_sync(~0u, layer * SEQ + (wg * 2 + ((g >> 1) & 1)) * 512 + (mb * 16 + 4 * (warp & 3) + (g >> 2)) * 2 + (g & 1), lane);
        mbar_wait(bar_wo, 0);
        if (wg) mbar_wait(bar_pv, 0);
        if (wg) asm volatile("bar.sync 2, 128;" ::: "memory"); else asm volatile("bar.sync 1, 128;" ::: "memory");
        TSTAMP2(2); CSA(8);
#pragma unroll
        for (int q = 0; q < 8; q++) {
            uint32_t bo = wo_off(0) >> 4;
            if (q) {
                mbar_wait(bar_f2 + 64 * wg + 8 * q, 0);
                asm volatile("ld.shared.u32 %0, [%1];" : "=r"(bo) : "r"(que + 32 * wg + 4 * q) : "memory");
                bo = __shfl_sync(~0u, bo, 0);
                TSTAMP4(q);
                if (q % 3 == 1) CSA(9 + q / 3);
                if (q == 1 && (tid & 127) == 0) DBGC(29 + 8 * wg);
            }
            wgmma_fence();
#pragma unroll
            for (int j = 0; j < 5; j++) wgmma_n80(ac2, (j < 4 ? da0 : da1) + (q == 7 ? o7 : 0u) + (uint64_t)((q < 6 ? q * 640 : 0) + (j & 2) * 16 + (j & 1) * 2), (j < 4 ? db0 : db1) + bo + (uint64_t)((j & 2) * 160 + (j & 1) * 32), j || q);
            wgmma_commit();
            if (q == 0) {
                wgmma_wait<0>();
                if ((tid & 127) == 0) { mbar_arrive(bar_e2 + 16 * wg); mbar_arrive(bar_e2 + 8); }
            }
            if (q == 2 && wg) {
                wgmma_wait<1>();
                if (tid == 128) mbar_arrive(bar_e2 + 24);
            }
        }
        if ((tid & 127) == 0) DBGC(28 + wg * 8 + 7);
        TSTAMP2(3);
        wgmma_wait<0>();
        TSTAMP2(4); CSA(12);
        if (__any_sync(~0u, ac2[0] != ac2[0] || ac2[2] != ac2[2])) {
#pragma unroll
            for (int i = 0; i < 40; i++) ac2[i] = 0.f;
            uint32_t a[20], an[20];
            auto lda = [&](uint32_t (&r)[20], int h) {
#pragma unroll
                for (int u = 0; u < 4; u++)
                    asm volatile("ld.relaxed.gpu.global.v4.u32 {%0,%1,%2,%3}, [%4];" : "=r"(r[4 * u]), "=r"(r[4 * u + 1]), "=r"(r[4 * u + 2]), "=r"(r[4 * u + 3]) : "l"(ot + h * 20480 + o0 + u * 512) : "memory");
#pragma unroll
                for (int u = 0; u < 2; u++)
                    asm volatile("ld.relaxed.gpu.global.v2.u32 {%0,%1}, [%2];" : "=r"(r[16 + 2 * u]), "=r"(r[17 + 2 * u]) : "l"(ot + h * 20480 + o1 + u * 256) : "memory");
            };
            lda(an, 0);
#pragma unroll 5
            for (int k = lane; k < WOB / 16; k += 32)
                reinterpret_cast<uint4*>(stg + (sl - sbase))[k] = __ldcg(reinterpret_cast<const uint4*>(wo + hg * 8 * WOB) + k);
            __syncwarp();
#pragma unroll 1
            for (int h = 0; h < 8; h++) {
#pragma unroll 1
                for (int it = 0; it < SPIN_MAX; it++) {
                    uint32_t m = 0;
#pragma unroll
                    for (int k = 0; k < 20; k += 2) m = __vimax3_u32(m, an[k], an[k + 1]);
                    if (!__any_sync(~0u, m == ~0u)) break;
                    lda(an, h);
                }
#pragma unroll
                for (int k = 0; k < 20; k++) a[k] = an[k];
                lda(an, min(h + 1, 7));
                const uint32_t bp = h == hg ? sl : sbase + wo_off(h + (h < hg));
                const int r0 = 8 * ((lane & 7) >> 1) + 2 * (lane >> 3) + (lane & 1), r2 = 4 * ((lane & 7) >> 1) + 2 * ((lane >> 3) & 1) + (lane & 1);
#pragma unroll
                for (int n = 0; n < 10; n++) {
                    uint32_t b[12];
                    ldsm_x4_t(b, bp + (n >> 1) * 1024 + r0 * 32 + (((n ^ (r0 >> 2)) & 1) << 4));
                    ldsm_x4_t(b + 4, bp + 5120 + (n >> 1) * 1024 + r0 * 32 + (((n ^ (r0 >> 2)) & 1) << 4));
                    ldsm_x4_t(b + 8, bp + 10240 + (n >> 1) * 512 + r2 * 32 + (((n ^ (r2 >> 2)) & 1) << 4));
                    mma_bf16(ac2 + 4 * n, a[0], a[8], a[1], a[9], b[0], b[1]); mma_bf16(ac2 + 4 * n, a[2], a[10], a[3], a[11], b[2], b[3]);
                    mma_bf16(ac2 + 4 * n, a[4], a[12], a[5], a[13], b[4], b[5]); mma_bf16(ac2 + 4 * n, a[6], a[14], a[7], a[15], b[6], b[7]);
                    mma_bf16(ac2 + 4 * n, a[16], a[18], a[17], a[19], b[8], b[9]);
                }
            }
        }
#pragma unroll
        for (int j = 0; j < 10; j++)
#pragma unroll
            for (int hh = 0; hh < 2; hh++) {
                const uint32_t a = pack2(ac2[4 * j + 2 * hh], ac2[4 * j + 2 * hh + 1]);
                const __nv_bfloat162 r = __hadd2_rn(*reinterpret_cast<const __nv_bfloat162*>(&xr[j][hh]), *reinterpret_cast<const __nv_bfloat162*>(&a));
                xr[j][hh] = *reinterpret_cast<const uint32_t*>(&r);
            }
        const uint32_t so = sl + 30720;
#pragma unroll
        for (int j = 0; j < 10; j += 2) stsm_x4_t(so + trow + 1024 * j, xr[j][0], xr[j][1], xr[j + 1][0], xr[j + 1][1]);
        if (wg) asm volatile("bar.sync 2, 128;" ::: "memory"); else asm volatile("bar.sync 1, 128;" ::: "memory");
        TSTAMP2(5); CSA(13);
        if ((tid & 127) == 0) {
            fence_async_smem();
            asm volatile("cp.async.bulk.tensor.2d.global.shared::cta.bulk_group [%0, {%1, %2}], [%3];" ::"l"(&tmX1), "r"(mb * 128 + 64 * wg), "r"(hg * 80), "r"(so) : "memory");
            asm volatile("cp.async.bulk.commit_group;" ::: "memory");
        }
        __syncwarp();
        const float p0 = *(volatile const float*)&rw[g].x, p1 = *(volatile const float*)&rw[g + 8].x;
        float s[3][4] = {};
        const uint32_t pp[2] = {__byte_perm(__float_as_uint(p0), 0, 0x3232), __byte_perm(__float_as_uint(p1), 0, 0x3232)};
#pragma unroll
        for (int j = 0; j < 10; j += 2) {
            const uint32_t d0 = sub2(xr[j][0], pp[0]), d1 = sub2(xr[j][1], pp[1]), d2 = sub2(xr[j + 1][0], pp[0]), d3 = sub2(xr[j + 1][1], pp[1]);
            mma_bf16(s[0], xr[j][0], xr[j][1], xr[j + 1][0], xr[j + 1][1], 0x3f803f80u, 0x3f803f80u);
            mma_bf16(s[1], d0, d1, d2, d3, d0, d2);
            mma_bf16(s[2], d0, d1, d2, d3, d1, d3);
        }
        if (t == (g >> 1)) {
            float2* rp = rsum + ri;
            asm volatile("red.relaxed.gpu.global.add.v2.f32 [%0], {%1, %2};" ::"l"(rp), "f"(fmaf(-80.f, p0, s[0][0])), "f"((g & 1) ? s[1][1] : s[1][0]) : "memory");
            asm volatile("red.relaxed.gpu.global.add.v2.f32 [%0], {%1, %2};" ::"l"(rp + 4), "f"(fmaf(-80.f, p1, s[0][2])), "f"((g & 1) ? s[2][3] : s[2][2]) : "memory");
        }
        asm volatile("cp.async.bulk.wait_group.read 0;" ::: "memory");
        TSTAMP2(6); CSA(14); CSA_END;
        if (tid == 0) DBGC(63);
        if (tid == 128) DBGC(28);
        if (tid == 0) DBGCAL(2);
        GSTAMP(g_tim1, 14);
        SPAN(1 + 4 * layer, 3);
    }
#undef layer
}

static int h_nsm;
static void* h_sym[11];
static TileTab h_tab[2];
static CUtensorMap h_tmX0, h_tmX1, h_tmR0, h_tmR1, h_tmX1st, h_tmOut;
static KgMaps h_tmW;
typedef CUresult (*PFN_encodeTiled)(CUtensorMap*, CUtensorMapDataType, cuuint32_t, void*, const cuuint64_t*, const cuuint64_t*,
                                    const cuuint32_t*, const cuuint32_t*, CUtensorMapInterleave, CUtensorMapSwizzle,
                                    CUtensorMapL2promotion, CUtensorMapFloatOOBfill);
static void make_tmap(CUtensorMap* tm, const void* ptr, uint64_t cols, uint64_t rows, uint32_t bc, uint32_t br, CUtensorMapSwizzle sw, uint64_t pitch = 0, uint64_t hi = 0, uint32_t bh = 2) {
    static PFN_encodeTiled fn = nullptr;
    if (!fn) {
        void* p = nullptr; cudaDriverEntryPointQueryResult qr;
        cudaGetDriverEntryPoint("cuTensorMapEncodeTiled", &p, cudaEnableDefault, &qr);
        fn = (PFN_encodeTiled)p;
    }
    if (br == 0) {
        cuuint64_t dims[5] = {16, 2, rows / 8, 4, cols / 16}; cuuint64_t strides[4] = {cols * 2, cols * 16, cols * 4, 32};
        cuuint32_t box[5] = {16, 2, bc, 4, 5}; cuuint32_t es[5] = {1, 1, 1, 1, 1};
        fn(tm, CU_TENSOR_MAP_DATA_TYPE_BFLOAT16, 5, const_cast<void*>(ptr), dims, strides, box, es, CU_TENSOR_MAP_INTERLEAVE_NONE, sw,
           CU_TENSOR_MAP_L2_PROMOTION_L2_128B, CU_TENSOR_MAP_FLOAT_OOB_FILL_NONE);
        return;
    }
    if (hi == 16) {
        cuuint64_t dims[4] = {16, 32, 120, 20}; cuuint64_t strides[3] = {3840, 32, 32 * 3840};
        cuuint32_t box[4] = {16, 32, 5, 2}; cuuint32_t es[4] = {1, 1, 1, 1};
        fn(tm, CU_TENSOR_MAP_DATA_TYPE_BFLOAT16, 4, const_cast<void*>(ptr), dims, strides, box, es, CU_TENSOR_MAP_INTERLEAVE_NONE, sw,
           CU_TENSOR_MAP_L2_PROMOTION_L2_128B, CU_TENSOR_MAP_FLOAT_OOB_FILL_NONE);
        return;
    }
    if (bh == 0) {
        cuuint64_t dims[5] = {64, 64, 2, 16, 10}; cuuint64_t strides[4] = {pitch * 2, hi * 2, cols * 2, rows * 2};
        cuuint32_t box[5] = {64, 64, 2, 1, 1}; cuuint32_t es[5] = {1, 1, 1, 1, 1};
        fn(tm, CU_TENSOR_MAP_DATA_TYPE_BFLOAT16, 5, const_cast<void*>(ptr), dims, strides, box, es, CU_TENSOR_MAP_INTERLEAVE_NONE, sw,
           CU_TENSOR_MAP_L2_PROMOTION_L2_128B, CU_TENSOR_MAP_FLOAT_OOB_FILL_NONE);
        return;
    }
    if (hi) {
        cuuint64_t dims[3] = {cols, rows, hi == 64 ? 32u : 2u}; cuuint64_t strides[2] = {pitch * 2, hi * 2};
        cuuint32_t box[3] = {bc, br, bh}; cuuint32_t es[3] = {1, 1, 1};
        fn(tm, CU_TENSOR_MAP_DATA_TYPE_BFLOAT16, 3, const_cast<void*>(ptr), dims, strides, box, es, CU_TENSOR_MAP_INTERLEAVE_NONE, sw,
           CU_TENSOR_MAP_L2_PROMOTION_L2_128B, CU_TENSOR_MAP_FLOAT_OOB_FILL_NONE);
        return;
    }
    cuuint64_t dims[2] = {cols, rows}; cuuint64_t strides[1] = {(pitch ? pitch : cols) * 2};
    cuuint32_t box[2] = {bc, br}; cuuint32_t es[2] = {1, 1};
    fn(tm, CU_TENSOR_MAP_DATA_TYPE_BFLOAT16, 2, const_cast<void*>(ptr), dims, strides, box, es, CU_TENSOR_MAP_INTERLEAVE_NONE, sw,
       CU_TENSOR_MAP_L2_PROMOTION_L2_128B, CU_TENSOR_MAP_FLOAT_OOB_FILL_NONE);
}
template <typename... Args>
static void launch_pdl(void (*kern)(Args...), int grid, int block, int smem, Args... args) {
    cudaLaunchConfig_t cfg = {};
    cfg.gridDim = dim3(grid); cfg.blockDim = dim3(block); cfg.dynamicSmemBytes = smem; cfg.stream = cudaStreamPerThread;
    cudaLaunchAttribute at[1];
    at[0].id = cudaLaunchAttributeProgrammaticStreamSerialization; at[0].val.programmaticStreamSerializationAllowed = 1;
    cfg.attrs = at; cfg.numAttrs = 1;
    cudaLaunchKernelEx(&cfg, kern, args...);
}
static void launch_stage(int k, void* const* d_in, void* d_out) {
    const Par par = {k > 1 ? nullptr : (const bf16*)d_in[4], (const bf16*)d_in[5], (const bf16*)d_in[6], (const bf16*)d_in[7], (const bf16*)d_in[8], (const bf16*)d_in[9], k > 1, 0, (const bf16*)d_in[0],
                     (uint4*)h_sym[4], (uint4*)h_sym[2], (uint4*)h_sym[6], (uint4*)h_sym[3], (uint4*)h_sym[0], (float*)h_sym[5], (uint4*)h_sym[1], (const bf16*)d_in[1], (const bf16*)d_in[2]};
    auto a1 = h_nsm == 132 ? a1_kernel<true> : a1_kernel<false>;
    switch (k) {
        case 1: a1<<<h_nsm, A1_THREADS, A1_SMEM, cudaStreamPerThread>>>(par, h_tmX0, h_tmR0, h_tmX1st, h_tmW, h_tab[0]); break;
        case 3: launch_pdl(conv_kernel, DM / CV_CPB, CV_THREADS, CV_SMEM, 0, (const uint4*)h_sym[7], (const float4*)h_sym[4], (const bf16*)h_sym[8], (bf16*)h_sym[9], (const uint4*)h_sym[0], h_tmOut); break;
        case 5: launch_pdl(a1, h_nsm, A1_THREADS, A1_SMEM, par, h_tmX1, h_tmR1, h_tmX1st, h_tmW, h_tab[1]); break;
        case 7: launch_pdl(conv_kernel, DM / CV_CPB, CV_THREADS, CV_SMEM, 1, (const uint4*)h_sym[7] + SEQ / 8, (const float4*)h_sym[4] + SEQ / 2, (const bf16*)h_sym[8], (bf16*)h_sym[10], (const uint4*)h_sym[0], h_tmOut); break;
        default: break;
    }
}
static int n_stage_kernels() { return 9; }
static const char* stage_name(int k) { const char* n[] = {"kgen", "a1", "a2", "conv", "tr", "a1", "a2", "conv", "tr"}; return n[k]; }

extern "C" void kernel_launch(void* const* d_in, const int* in_sizes, int n_in, void* d_out, int out_size) {
    (void)in_sizes; (void)n_in; (void)out_size;
    static const void *p_in = nullptr, *p_w1 = nullptr, *p_w2 = nullptr, *p_out = nullptr;
    if (p_in != d_in[0] || p_w1 != d_in[1] || p_w2 != d_in[2] || p_out != d_out) {
        cudaFuncSetAttribute(conv_kernel, cudaFuncAttributeMaxDynamicSharedMemorySize, CV_SMEM);
        cudaFuncSetAttribute(a1_kernel<true>, cudaFuncAttributeMaxDynamicSharedMemorySize, A1_SMEM);
        cudaFuncSetAttribute(a1_kernel<false>, cudaFuncAttributeMaxDynamicSharedMemorySize, A1_SMEM);
        int dev; cudaGetDevice(&dev); cudaDeviceGetAttribute(&h_nsm, cudaDevAttrMultiProcessorCount, dev);
        if (h_nsm != 132) h_nsm = 128;
        cudaGetSymbolAddress(&h_sym[0], g_tap); cudaGetSymbolAddress(&h_sym[1], g_wq); cudaGetSymbolAddress(&h_sym[2], g_wo);
        cudaGetSymbolAddress(&h_sym[3], g_halo); cudaGetSymbolAddress(&h_sym[4], g_sum); cudaGetSymbolAddress(&h_sym[5], g_csp); cudaGetSymbolAddress(&h_sym[6], g_of);
        cudaGetSymbolAddress(&h_sym[7], g_piv); cudaGetSymbolAddress(&h_sym[8], g_x1T); cudaGetSymbolAddress(&h_sym[9], g_xcT); cudaGetSymbolAddress(&h_sym[10], g_yT);
        for (int i = 0; i < 264; i++) {
            const int s = i % 132, h = (s - 64) >> 1;
            const int t = h_nsm != 132 ? s : s < 64 ? ((s >> 1) & 7) * 16 + (s >> 4) * 2 + (s & 1) : s < 120 ? (1 + h % 7) * 16 + 8 + (h / 7) * 2 + (s & 1) : s < 124 ? 128 : s - 116;
            const int hg = (4 * (t >> 6) + (t & 3)) & 7;
            const uint64_t wp = (uint64_t)h_sym[1] + hg * 10 * WQ_STAGE;
            h_tab[i / 132].e[s] = make_uint4((uint32_t)wp, (uint32_t)(wp >> 32), ((t >> 2) & 15) | (i / 132) << 4 | hg << 8 | 5 * (hg >> 2) << 16 | (uint32_t)t << 24, 0);
        }
        void *px1, *px2;
        cudaGetSymbolAddress(&px1, g_x1T); cudaGetSymbolAddress(&px2, g_xcT);
        make_tmap(&h_tmX0, d_in[0], 128 * 640, 64, 64, 64, CU_TENSOR_MAP_SWIZZLE_128B, 1280, 640, 0);
        make_tmap(&h_tmX1, px2, 128, 64 * XCP, 64, 64, CU_TENSOR_MAP_SWIZZLE_128B, XCP, 64, 0);
        make_tmap(&h_tmR0, d_in[0], 640, 1024, 80, 64, CU_TENSOR_MAP_SWIZZLE_NONE, 1280, 640, 1);
        make_tmap(&h_tmR1, px2, 64, 640, 64, 80, CU_TENSOR_MAP_SWIZZLE_128B, XCP, 64, 1);
        make_tmap(&h_tmX1st, px1, 2048, 640, 64, 80, CU_TENSOR_MAP_SWIZZLE_128B, XCP);
        make_tmap(&h_tmW.q, d_in[1], 16, 640, 16, 32, CU_TENSOR_MAP_SWIZZLE_32B, 1920, 16, 5);
        make_tmap(&h_tmW.o, d_in[2], 640, 640, 4, 0, CU_TENSOR_MAP_SWIZZLE_32B);
        make_tmap(&h_tmW.t, d_in[2], 640, 640, 2, 0, CU_TENSOR_MAP_SWIZZLE_32B);
        make_tmap(&h_tmOut, d_out, 640, 1024, 80, 8, CU_TENSOR_MAP_SWIZZLE_NONE, 1280, 640, 1);
        p_in = d_in[0]; p_w1 = d_in[1]; p_w2 = d_in[2]; p_out = d_out;
    }
    for (int k = 0; k < n_stage_kernels(); k++) launch_stage(k, d_in, d_out);
}
```

```cpp
#include <cuda_runtime.h>
#include <cuda_bf16.h>
#include <cuda_fp16.h>
#include <stdint.h>
#include <cuda.h>

typedef __nv_bfloat16 bf16;

constexpr int SEQ = 2048;
constexpr int DM = 640;
constexpr int NMODE = 192;

__device__ __forceinline__ float bf2f(bf16 v) { return __bfloat162float(v); }
__device__ __forceinline__ float rbf(float v) {
    uint32_t r;
    asm("cvt.rn.bf16x2.f32 %0, %1, %2;" : "=r"(r) : "f"(v), "f"(0.f));
    return __uint_as_float(r);
}
__device__ __forceinline__ uint32_t pack2(float lo, float hi) {
    __nv_bfloat162 t = __floats2bfloat162_rn(lo, hi);
    return *reinterpret_cast<uint32_t*>(&t);
}
__device__ __forceinline__ void pdl_sync() {
    asm volatile("griddepcontrol.wait;" ::: "memory");
    asm volatile("griddepcontrol.launch_dependents;" ::: "memory");
}
__device__ __forceinline__ float sqrt_apx(float v) { float r; asm("sqrt.approx.ftz.f32 %0, %1;" : "=f"(r) : "f"(v)); return r; }
__device__ __forceinline__ float rcp_apx(float v) { float r; asm("rcp.approx.ftz.f32 %0, %1;" : "=f"(r) : "f"(v)); return r; }
__device__ __forceinline__ uint32_t smem_u32(const void* p) { return (uint32_t)__cvta_generic_to_shared(p); }

constexpr int TAPB = 2944, TAPE = 928;
__device__ __align__(128) uint4 g_tap[DM * TAPB / 16];
#define XPAD 64
constexpr int XCP = SEQ + XPAD;
__device__ __align__(128) bf16 g_x1T[DM * XCP];
__device__ __align__(128) bf16 g_xcT[DM * XCP];
__device__ __align__(128) uint4 g_of[128 * 1280];
constexpr int WQ_STAGE = 240 * 128, WOB = 80 * 160;
__device__ __align__(128) uint4 g_wq[8 * 10 * WQ_STAGE / 16];
__device__ __align__(128) uint4 g_wo[64 * WOB / 16];
__device__ __align__(128) uint4 g_xb[128 * 240];
__device__ __align__(16) float g_csp[10 * 1920];
#define FSTR 32
__device__ __align__(128) float2 g_sum[2 * SEQ + 256 * FSTR];
__device__ __align__(16) bf16 g_piv[2 * SEQ];
__device__ __align__(128) bf16 g_yT[DM * XCP];
__device__ uint32_t g_epoch;
__device__ __align__(16) unsigned long long g_rstat[SEQ];
__device__ __align__(128) uint4 g_halo[640 * 148];
__device__ __forceinline__ unsigned long long tagw(uint32_t payload, uint32_t tag) { return ((unsigned long long)tag << 32) | payload; }
__device__ __forceinline__ ulonglong2 ld_tag2(const ulonglong2* p) {
    ulonglong2 v;
    asm volatile("ld.relaxed.gpu.global.v2.u64 {%0, %1}, [%2];" : "=l"(v.x), "=l"(v.y) : "l"(p) : "memory");
    return v;
}
__device__ __forceinline__ bool tag_ok(ulonglong2 v, uint32_t tag) { return (uint32_t)(v.x >> 32) == tag && (uint32_t)(v.y >> 32) == tag; }
__device__ __forceinline__ uint32_t ld_epoch() { uint32_t v; asm volatile("ld.relaxed.gpu.global.u32 %0, [%1];" : "=r"(v) : "l"(&g_epoch) : "memory"); return v + 1; }
constexpr int SPIN_MAX = 1 << 20;
__device__ __align__(128) uint32_t g_started[128];
__device__ __forceinline__ void sm_started(int slot) { asm volatile("red.relaxed.gpu.global.add.u32 [%0], 1;" ::"l"(g_started + slot) : "memory"); }
__device__ __forceinline__ void publish(int slot) {
    asm volatile("fence.proxy.async.global;" ::: "memory");
    asm volatile("red.release.gpu.global.add.u32 [%0], 1;" ::"l"(g_started + slot) : "memory");
}
__device__ __forceinline__ void await_all(int slot, uint32_t want) {
#pragma unroll 1
    for (int it = 0; it < SPIN_MAX; it++) {
        uint32_t v;
        asm volatile("ld.acquire.gpu.global.u32 %0, [%1];" : "=r"(v) : "l"(g_started + slot) : "memory");
        if (__all_sync(~0u, (int)(v - want) >= 0)) break;
        __nanosleep(50);
    }
    asm volatile("fence.proxy.async.global;" ::: "memory");
}
__device__ __noinline__ void sm_idle(int slot) {
    if (threadIdx.x != 288) return;
    asm volatile("fence.acq_rel.gpu;" ::: "memory");
    asm volatile("fence.proxy.async.global;" ::: "memory");
    sm_started(slot);
    const uint32_t want = ld_epoch() * gridDim.x;
    pdl_sync();
#pragma unroll 1
    for (int it = 0; it < SPIN_MAX; it++) {
        uint32_t v;
        asm volatile("ld.relaxed.gpu.global.u32 %0, [%1];" : "=r"(v) : "l"(g_started + slot) : "memory");
        if ((int)(v - want) >= 0) break;
        __nanosleep(100);
    }
}
struct TileTab { uint4 e[132]; };
__device__ __forceinline__ bool elect() {
    uint32_t p;
    asm volatile("{\n.reg .pred p;\nelect.sync _|p, 0xffffffff;\nselp.b32 %0, 1, 0, p;\n}" : "=r"(p));
    return p;
}
#define DBG_SYMS
#define TSTAMP(i)
#define TSTAMP1(i)
#define TSTAMP1T(i, t)
#define TSTAMP1X(i, t)
#define SPAN(k, i)
#define GSTAMP(arr, i)
#define TSTAMP2(i)
#define TSTAMP3(i)
#define TSTAMP4(i)
#define TSTAMPK(i, t)
#define TSTAMPC(i)
#define DBGC(i)
#define DBGV(i, v)
#define DBGCAL(i)

#define CSK(i)
#define CSK_END
#define CSA(i)
#define CSA_END
#define CST(i)
#define CST_END
#define CST_EXTRA 0
__device__ __forceinline__ void mma_bf16(float* d, uint32_t a0, uint32_t a1, uint32_t a2, uint32_t a3, uint32_t b0, uint32_t b1) {
    asm volatile("mma.sync.aligned.m16n8k16.row.col.f32.bf16.bf16.f32 {%0,%1,%2,%3}, {%4,%5,%6,%7}, {%8,%9}, {%0,%1,%2,%3};"
                 : "+f"(d[0]), "+f"(d[1]), "+f"(d[2]), "+f"(d[3]) : "r"(a0), "r"(a1), "r"(a2), "r"(a3), "r"(b0), "r"(b1));
}
__device__ __forceinline__ void mma_bf16_k8(float* d, uint32_t a0, uint32_t a1, uint32_t b0) {
    asm volatile("mma.sync.aligned.m16n8k8.row.col.f32.bf16.bf16.f32 {%0,%1,%2,%3}, {%4,%5}, {%6}, {%0,%1,%2,%3};"
                 : "+f"(d[0]), "+f"(d[1]), "+f"(d[2]), "+f"(d[3]) : "r"(a0), "r"(a1), "r"(b0));
}
__device__ __forceinline__ void ldsm_x4(uint32_t* r, uint32_t addr) {
    asm volatile("ldmatrix.sync.aligned.m8n8.x4.shared.b16 {%0,%1,%2,%3}, [%4];"
                 : "=r"(r[0]), "=r"(r[1]), "=r"(r[2]), "=r"(r[3]) : "r"(addr));
}

__device__ __forceinline__ void ldsm_x4_t(uint32_t* r, uint32_t addr) {
    asm volatile("ldmatrix.sync.aligned.m8n8.x4.trans.shared.b16 {%0,%1,%2,%3}, [%4];"
                 : "=r"(r[0]), "=r"(r[1]), "=r"(r[2]), "=r"(r[3]) : "r"(addr));
}
__device__ __forceinline__ void mbar_init(uint32_t bar, int count) { asm volatile("mbarrier.init.shared::cta.b64 [%0], %1;" ::"r"(bar), "r"(count)); }
__device__ __forceinline__ void mbar_arrive(uint32_t bar) { asm volatile("mbarrier.arrive.shared::cta.b64 _, [%0];" ::"r"(bar) : "memory"); }
__device__ __forceinline__ void mbar_wait(uint32_t bar, uint32_t parity) {
    asm volatile("{\n.reg .pred p;\nWAIT_LOOP:\n"
                 "mbarrier.try_wait.parity.shared::cta.b64 p, [%0], %1;\n"
                 "@p bra.uni WAIT_DONE;\nbra.uni WAIT_LOOP;\nWAIT_DONE:\n}" ::"r"(bar), "r"(parity) : "memory");
}

__device__ __forceinline__ void mbar_expect_tx(uint32_t bar, uint32_t bytes) {
    asm volatile("mbarrier.arrive.expect_tx.shared::cta.b64 _, [%0], %1;" ::"r"(bar), "r"(bytes) : "memory");
}
__device__ __forceinline__ void tma_load_2d(uint32_t dst, const void* tmap, int c0, int c1, uint32_t bar) {
    asm volatile("cp.async.bulk.tensor.2d.shared::cluster.global.mbarrier::complete_tx::bytes [%0], [%1, {%3, %4}], [%2];"
                 ::"r"(dst), "l"(tmap), "r"(bar), "r"(c0), "r"(c1) : "memory");
}
__device__ __forceinline__ void tma_load_3d(uint32_t dst, const void* tmap, int c0, int c1, int c2, uint32_t bar) {
    asm volatile("cp.async.bulk.tensor.3d.shared::cluster.global.mbarrier::complete_tx::bytes [%0], [%1, {%3, %4, %5}], [%2];"
                 ::"r"(dst), "l"(tmap), "r"(bar), "r"(c0), "r"(c1), "r"(c2) : "memory");
}
__device__ __forceinline__ void fence_async_smem() { asm volatile("fence.proxy.async.shared::cta;" ::: "memory"); }
__device__ __forceinline__ void bulk_load(uint32_t dst, const void* src, uint32_t bytes, uint32_t bar) {
    asm volatile("cp.async.bulk.shared::cluster.global.mbarrier::complete_tx::bytes [%0], [%1], %2, [%3];"
                 ::"r"(dst), "l"(src), "r"(bytes), "r"(bar) : "memory");
}
__device__ __forceinline__ void stsm_x4(uint32_t addr, uint32_t r0, uint32_t r1, uint32_t r2, uint32_t r3) {
    asm volatile("stmatrix.sync.aligned.m8n8.x4.shared.b16 [%0], {%1,%2,%3,%4};" ::"r"(addr), "r"(r0), "r"(r1), "r"(r2), "r"(r3) : "memory");
}
__device__ __forceinline__ void stsm_x4_t(uint32_t addr, uint32_t r0, uint32_t r1, uint32_t r2, uint32_t r3) {
    asm volatile("stmatrix.sync.aligned.m8n8.x4.trans.shared.b16 [%0], {%1,%2,%3,%4};" ::"r"(addr), "r"(r0), "r"(r1), "r"(r2), "r"(r3) : "memory");
}
__device__ __forceinline__ void prefetch_tmap(const void* tmap) { asm volatile("prefetch.tensormap [%0];" ::"l"(tmap) : "memory"); }

__device__ __forceinline__ float2 cexp_at(float wr2, float wi, float p) {
    float er;
    asm("ex2.approx.ftz.f32 %0, %1;" : "=f"(er) : "f"(wr2 * p));
    float th = wi * p;
    const float k = rintf(th * 0.15915494309189535f);
    th = fmaf(k, -6.2831854820251465f, th);
    th = fmaf(k, 1.7484555314695172e-7f, th);
    return make_float2(er * __cosf(th), er * __sinf(th));
}
__device__ __forceinline__ float2 cmul(float2 a, float2 b) {
    return make_float2(fmaf(a.x, b.x, -a.y * b.y), fmaf(a.x, b.y, a.y * b.x));
}
__device__ __forceinline__ float2 csqr(float2 a) { return make_float2(fmaf(a.x, a.x, -a.y * a.y), (a.x + a.x) * a.y); }
__device__ __forceinline__ uint32_t packh(float2 v) {
    uint32_t r;
    asm("cvt.rn.f16x2.f32 %0, %1, %2;" : "=r"(r) : "f"(v.y), "f"(v.x));
    return r;
}
__device__ __forceinline__ uint2 packr(float2 v) { return make_uint2(packh(v), packh(make_float2(-v.y, v.x))); }
__device__ __forceinline__ uint32_t hcmul(uint32_t a, uint2 b) {
    const __half2 x = *reinterpret_cast<const __half2*>(&a);
    const __half2 r = __hfma2(__high2half2(x), *reinterpret_cast<const __half2*>(&b.y), __hmul2(__low2half2(x), *reinterpret_cast<const __half2*>(&b.x)));
    return *reinterpret_cast<const uint32_t*>(&r);
}

struct Par { const bf16 *logA, *Aim, *Cre, *Cim, *logdt, *dsk; int layer, pad; const bf16* x; uint4 *sum, *wop, *of, *halo, *tap; float* csp; uint4* wq; const bf16 *wqkv, *wo; };
struct KgMaps { CUtensorMap q, o, t; };

__device__ __forceinline__ void bulk_prefetch(const void* p, uint32_t bytes) { asm volatile("cp.async.bulk.prefetch.L2.global [%0], %1;" ::"l"(p), "r"(bytes) : "memory"); }
__device__ __forceinline__ void bulk_store(void* dst, uint32_t src, uint32_t bytes) { asm volatile("cp.async.bulk.global.shared::cta.bulk_group [%0], [%1], %2;" ::"l"(dst), "r"(src), "r"(bytes) : "memory"); }
__device__ __forceinline__ void kgen_first(const Par& in, const KgMaps& tm, const uint32_t b0, const uint32_t wbar, const bool one) {
    const uint32_t blk = blockIdx.x, sec = (blk >= 40) + (blk >= 80), it = (blk >> 3) - 5 * sec, up = (blk >> 2) & 1, hi = blk >> 6;
    auto fetch = [&](int h) {
        if (blk < 120) asm volatile("cp.async.bulk.tensor.4d.shared::cluster.global.mbarrier::complete_tx::bytes [%0], [%1, {%3, %3, %4, %5}], [%2];"
                                    ::"r"(b0 + 10240 * h), "l"(&tm.q), "r"(wbar + 8 * h), "r"(0), "r"(sec * 40 + (blk & 7) * 5), "r"(2 * it + 10 * (up ^ h)) : "memory");
    };
    auto fetch_o = [&](int i) {
        asm volatile("cp.async.bulk.tensor.5d.shared::cluster.global.mbarrier::complete_tx::bytes [%0], [%1, {%3, %3, %4, %3, %5}], [%2];"
                     ::"r"(b0 + 20480 + i * 5120), "l"(&tm.o + i), "r"(wbar + 16), "r"(0), "r"((blk & 7) * 10 + (hi + i) * 4), "r"(((blk >> 3) & 7) * 5) : "memory");
    };
    if (one) {
#pragma unroll
        for (int i = 0; i < 3; i++) mbar_init(wbar + 8 * i, 1);
        asm volatile("fence.mbarrier_init.release.cluster;" ::: "memory");
        fetch(0);
    }
    __syncwarp();
    if (blk >> 20) __trap();
    if (one) {
        bulk_prefetch(in.wqkv + blk * 9600, 19200);
        fetch(1);
        bulk_prefetch(in.wo + blk * 3200, 6400);
        fetch_o(0);
        if (hi) fetch_o(1);
        mbar_expect_tx(wbar, 10240); mbar_expect_tx(wbar + 8, 10240); mbar_expect_tx(wbar + 16, 5120 + hi * 2560);
        bulk_prefetch(in.x + blk * 10240, 20480);
    }
}
template <typename F>
__device__ __forceinline__ void kgen_side(const Par& in, const uint32_t b0, const uint32_t wbar, F&& then) {
    const uint32_t blk = blockIdx.x, sec = (blk >= 40) + (blk >= 80), it = (blk >> 3) - 5 * sec, cg = (blk >> 3) & 7, hb = blk & 7;
    unsigned char* dst = reinterpret_cast<unsigned char*>(in.wq) + (hb * 10 + it) * WQ_STAGE + sec * 5120;
    unsigned char* dso = reinterpret_cast<unsigned char*>(in.wop) + (cg * 8 + (hb == cg ? 0 : hb + (hb < cg))) * WOB + (blk >> 6) * 5120;
    if (blk < 120) {
        mbar_wait(wbar, 0);
        CSK(2);
        bulk_store(dst, b0, 5120); bulk_store(dst + 15360, b0 + 5120, 5120);
        mbar_wait(wbar + 8, 0);
        CSK(3);
        bulk_store(dst + 5 * WQ_STAGE, b0 + 10240, 5120); bulk_store(dst + 5 * WQ_STAGE + 15360, b0 + 15360, 5120);
        asm volatile("cp.async.bulk.commit_group;" ::: "memory");
        asm volatile("cp.async.bulk.wait_group 0;" ::: "memory");
    }
    CSK(4);
    publish(32);
    CSK(5);
    if (blk < 128) {
        mbar_wait(wbar + 16, 0);
        bulk_store(dso, b0 + 20480, blk < 64 ? 5120 : 7680);
        asm volatile("cp.async.bulk.commit_group;" ::: "memory");
    }
    then();
    asm volatile("cp.async.bulk.wait_group 0;" ::: "memory");
}
__device__ __forceinline__ void kgen_sums(const Par& in, const uint32_t b0, const int h) {
    const int lane = threadIdx.x & 31, blk = blockIdx.x;
    if (blk < 120) {
        float cs[5][4] = {};
#pragma unroll
        for (int a = 0; a < 4; a++)
#pragma unroll
            for (int j = 0; j < 5; j++) {
                uint32_t w[4];
                ldsm_x4_t(w, b0 + h * 10240 + j * 1024 + ((lane >> 4) * 8 + (lane & 7)) * 32 + ((((lane >> 3) ^ (lane >> 2)) & 1) << 4) + (a >> 1) * 5120 + (a & 1) * 512);
                mma_bf16(cs[j], w[0], w[1], w[2], w[3], 0x3f803f80u, 0x3f803f80u);
            }
#pragma unroll
        for (int j = 0; j < 5; j++)
            if ((lane & 3) < 2) in.csp[(blk + 120 * h) * 80 + j * 16 + (lane >> 2) + 8 * (lane & 3)] = (lane & 3) ? cs[j][2] : cs[j][0];
    }
}
struct KgPar { uint32_t pw[4], ph[4], pdt, pdsk; };
__device__ __forceinline__ void kgen_load(const Par& in, const int w11, KgPar& k) {
    const uint32_t o = blockIdx.x * 480 + min(w11 * 48, w11 * 32 + 128), ow = o + (threadIdx.x & 31), oh = o + ow + (w11 < 8 ? 64 : 0);
    k.pdt = reinterpret_cast<const unsigned short*>(in.logdt)[ow / 96];
    k.pdsk = reinterpret_cast<const unsigned short*>(in.dsk)[ow / 96];
#pragma unroll
    for (int i = 0; i < 4; i++) {
        const bf16* p = i == 0 ? in.logA : i == 1 ? in.Aim : i == 2 ? in.Cre : in.Cim;
        k.pw[i] = reinterpret_cast<const uint32_t*>(p)[ow]; k.ph[i] = reinterpret_cast<const unsigned short*>(p)[oh];
    }
}
__device__ __forceinline__ void kgen_tables(const Par& in, uint4* tabs, const int w11, const KgPar& kp) {
    const int lane = threadIdx.x & 31, grp = min(w11 >> 1, 4), warp = w11 - 2 * grp;
    const int blk = blockIdx.x, d = blk * 5 + grp, tid = warp * 32 + lane;
    uint4* tab = tabs + grp * (2 * 256);
    const uint32_t *pw = kp.pw, *ph = kp.ph;
#pragma unroll
    for (int i = 0; i < 3; i++)
        if (i < 2 || w11 * 32 + lane < 36) asm volatile("st.global.v4.u32 [%0], {%1,%1,%1,%1};" ::"l"(in.halo + blk * 740 + w11 * 32 + lane + 352 * i), "r"(~0u));
    __syncwarp();
    if (w11 == 10) {
        if (lane < 16) in.sum[blk * 16 + lane] = make_uint4(0, 0, 0, 0);
        else if (lane < 20) reinterpret_cast<uint32_t*>(in.sum + 2048)[(blk * 4 + lane - 16) * FSTR] = 0;
    } else if (w11 > 1) asm volatile("bar.arrive 9, 352;" ::: "memory");
#pragma unroll
    for (int i = 0; i < 6; i++) tabs[w11 * 256 + 32 * i + lane] = make_uint4(0, 0, 0, 0);
    __syncwarp();
    CSK(1);
    const uint32_t tw = smem_u32(tabs) + w11 * 4096;
    const int g = lane >> 2, t = lane & 3;
    const int mt = lane >> 3, r = lane & 7;
    const uint32_t st1 = tw + mt * 1024 + r * 16, st2 = tw + (mt & 1) * 1024 + (mt >> 1) * 128 + ((r ^ (mt >> 1)) << 4), st3 = tw + 2048 + mt * 128 + ((r ^ mt) << 4);
    const uint32_t lda = tw + (mt & 1) * 1024 + r * 128 + (((mt >> 1) ^ r) << 4), ldb = tw + (mt >> 1) * 1024 + r * 128 + (((mt & 1) ^ r) << 4), ldc = tw + 2048 + r * 128 + ((mt ^ r) << 4);
    auto ldsm = [](uint32_t* v, uint32_t a) {
        asm volatile("ldmatrix.sync.aligned.m8n8.x4.shared.b16 {%0,%1,%2,%3}, [%4];" : "=r"(v[0]), "=r"(v[1]), "=r"(v[2]), "=r"(v[3]) : "r"(a) : "memory");
    };
    auto mma = [](float* c, const uint32_t* a, const uint32_t* b) {
        asm("mma.sync.aligned.m16n8k16.row.col.f32.f16.f16.f32 {%0,%1,%2,%3}, {%4,%5,%6,%7}, {%8,%9}, {%0,%1,%2,%3};"
            : "+f"(c[0]), "+f"(c[1]), "+f"(c[2]), "+f"(c[3]) : "r"(a[0]), "r"(a[1]), "r"(a[2]), "r"(a[3]), "r"(b[0]), "r"(b[1]));
    };
    asm volatile("st.shared.u32 [%0], %1;" ::"r"(tw + 3072), "r"(st1 ^ st2 ^ st3 ^ lda ^ ldb ^ ldc) : "memory");
    if (in.pad) __trap();
    const float dt = rbf(expf(__uint_as_float(kp.pdt << 16)));
    const uint32_t cm = __vmaxu2(__vmaxu2(pw[2] & 0x7fff7fffu, pw[3] & 0x7fff7fffu), __byte_perm(ph[2], ph[3], 0x5410) & 0x7fff7fffu);
    const int ex = min(max((int)(__float_as_uint(__uint_as_float(__reduce_max_sync(~0u, max(cm << 16, cm & 0xffff0000u))) * dt) >> 23), 20), 240);
    const float scale = __uint_as_float((uint32_t)(127 + 10 + 127 - ex) << 23), unscale = 2.0f * __uint_as_float((uint32_t)(ex - 10) << 23);
    float k2048 = 0.f;
    float acc[5][4] = {};
    uint32_t af[4][4] = {};
    auto rest = [&] {
        uint32_t b[4][4], c[8];
#pragma unroll
        for (int k = 0; k < 4; k++) {
            ldsm(b[k], ldb ^ (k << 5));
            if (!(k & 1)) ldsm(c + 2 * k, ldc ^ (k << 5));
        }
#pragma unroll
        for (int k = 0; k < 4; k++) { mma(acc[2], af[k], b[k]); mma(acc[3], af[k], b[k] + 2); mma(acc[4], af[k], c + 2 * k); }
    };
#pragma unroll 1
    for (uint32_t sel = 0x1076; sel < (grp < 4 ? 0x6000u : 0x4000u); sel += 0x2200) {
        rest();
        auto par = [&](int i) { return __uint_as_float(__byte_perm(pw[i], ph[i], sel)); };
        const float wr2 = -rbf(expf(par(0))) * dt * 1.4426950408889634f, wi = par(1) * dt;
        const float2 y1 = cexp_at(wr2, -wi, 1.f), z8 = cexp_at(wr2, wi, 8.f), y128 = cexp_at(wr2, -wi, 128.f);
        float2 h0 = make_float2(1.f, 0.f), g0 = make_float2(par(2) * dt * scale, -par(3) * dt * scale);
        const float2 v2 = csqr(y128), v3 = cmul(v2, y128), v4 = csqr(v2), v8 = csqr(v4), c8 = cmul(g0, v8);
        const uint2 z64 = packr(csqr(csqr(csqr(z8)))), v[8] = {make_uint2(packh(c8), 0u), packr(y128), packr(v2), packr(v3), packr(v4), packr(cmul(v4, y128)), packr(csqr(v3)), packr(cmul(v4, v3))};
        k2048 += fmaf(c8.x, v8.x, -c8.y * v8.y);
        uint32_t ge[4];
#pragma unroll
        for (int e = 0; e < 8; e++) {
            const uint32_t p = packh(h0), q = packh(g0);
            if (!(e & 1)) ge[e >> 1] = q;
            stsm_x4((st1 ^ (e << 4)) + e * 128, p, e ? hcmul(p, z64) : z64.x, q, hcmul(q, v[1]));
            if (e < 7) { h0 = e ? cmul(h0, z8) : z8; g0 = cmul(g0, y1); }
        }
        __syncwarp();
        uint32_t b[4][4];
#pragma unroll
        for (int k = 0; k < 4; k++) { ldsm(af[k], lda ^ (k << 5)); ldsm(b[k], (ldb ^ (k << 5)) + 2048); }
#pragma unroll
        for (int e = 0; e < 8; e += 2) {
            stsm_x4((st2 ^ (e << 4)) + e * 128, hcmul(ge[e & 3], v[2 + (e >> 2)]), hcmul(ge[0], v[4 + (e >> 1)]), hcmul(ge[(e & 3) + 1], v[2 + (e >> 2)]), hcmul(ge[2], v[4 + (e >> 1)]));
            if (!(e & 3)) stsm_x4((st3 ^ (e << 4)) + e * 128, e ? hcmul(v[0].x, v[e]) : v[0].x, hcmul(v[0].x, v[e + 1]), hcmul(v[0].x, v[e + 2]), hcmul(v[0].x, v[e + 3]));
            mma(acc[0], af[e >> 1], b[e >> 1]);
            mma(acc[1], af[e >> 1], b[e >> 1] + 2);
        }
        __syncwarp();
        if (sel == 0x1076) CSK(3);
    }
    rest();
#pragma unroll
    for (int e = 0; e < 5; e++) k2048 += __shfl_xor_sync(~0u, k2048, 1 << e);
    {
        float* Pp = reinterpret_cast<float*>(tab + warp * 256);
        auto sw = [](int i) { return i ^ ((i >> 2) & 24); };
#pragma unroll
        for (int h = 0; h < 2; h++) {
            const int b = g + 8 * h;
            *reinterpret_cast<float2*>(Pp + sw(8 * b + 2 * t)) = make_float2(acc[0][2 * h] * unscale, acc[0][2 * h + 1] * unscale);
            *reinterpret_cast<float2*>(Pp + 128 + sw(8 * b + 2 * t)) = make_float2(acc[1][2 * h] * unscale, acc[1][2 * h + 1] * unscale);
            *reinterpret_cast<float2*>(Pp + 256 + sw(4 * b + 2 * (t & 1) + 64 * (t >> 1))) = make_float2(acc[2][2 * h] * unscale, acc[2][2 * h + 1] * unscale);
            *reinterpret_cast<float2*>(Pp + 384 + sw(2 * b + 32 * t)) = make_float2(acc[3][2 * h] * unscale, acc[3][2 * h + 1] * unscale);
            Pp[512 + sw(b + 32 * t)] = acc[4][2 * h] * unscale;
            Pp[512 + sw(b + 32 * t + 16)] = acc[4][2 * h + 1] * unscale;
        }
        if (lane == 0) Pp[640] = k2048 * unscale;
    }
    CSK(4);
    asm volatile("bar.sync %0, %1;" ::"r"(grp + 4), "r"(grp < 4 ? 64 : 96) : "memory");
    if (warp == 2) return;
    const float* Kp = reinterpret_cast<const float*>(tab);
    auto ksum = [&](int i) -> float { return rbf(Kp[i] + Kp[1024 + i] + (grp < 4 ? 0.f : Kp[2048 + i])); };
    auto ksum2 = [&](int q) -> float2 {
        q ^= (q >> 2) & 12;
        const float2 a = reinterpret_cast<const float2*>(Kp)[q], b = reinterpret_cast<const float2*>(Kp)[512 + q];
        const float2 c = grp < 4 ? make_float2(0.f, 0.f) : reinterpret_cast<const float2*>(Kp)[1024 + q];
        return make_float2(a.x + b.x + c.x, a.y + b.y + c.y);
    };
    {
        uint2* W2 = reinterpret_cast<uint2*>(in.tap + d * (TAPB / 16)) + 8;
        uint2* E4 = W2 + (TAPE - 64) / 8;
        float2 v = ksum2(64 * warp + lane), z = ksum2(64 * warp + 32 + lane), y = ksum2(128 + tid);
        const int q = (96 + tid) ^ (((96 + tid) >> 2) & 6);
        const float4 ua = reinterpret_cast<const float4*>(Kp)[q], uc = reinterpret_cast<const float4*>(Kp)[256 + q], ud = grp < 4 ? make_float4(0.f, 0.f, 0.f, 0.f) : reinterpret_cast<const float4*>(Kp)[512 + q];
        const float4 ub = make_float4(uc.x + ud.x, uc.y + ud.y, uc.z + ud.z, uc.w + ud.w);
        const float s1 = ksum(tid == 31 ? 336 : lane ? 384 : 103), s2 = ksum(tid == 31 ? 512 : tid ? 640 : 231);
        if (tid == 0) v.x += __uint_as_float(kp.pdsk << 16);
        if (tid == 63) y.y -= s1;
        const uint32_t lo = pack2(v.x, v.y), hi = pack2(z.x, z.y), tp = pack2(y.x, y.y);
        uint32_t nl = __shfl_sync(~0u, lo, lane - 1), nh = __shfl_sync(~0u, lane == 31 ? lo : hi, lane - 1), nt = __shfl_sync(~0u, tp, lane + 1);
        if (lane == 0) nl = warp ? __float_as_uint(s1) : 0u;
        if (lane == 31) nt = warp ? 0u : __float_as_uint(s1) >> 16;
        W2[64 * warp + lane] = make_uint2(__byte_perm(lo, nl, 0x7610), __byte_perm(lo, 0, 0x1032));
        W2[64 * warp + lane + 32] = make_uint2(__byte_perm(hi, nh, 0x7610), __byte_perm(hi, 0, 0x1032));
        reinterpret_cast<uint4*>(W2)[64 + tid] = make_uint4(__byte_perm(tp, __float_as_uint(s2), tid ? 0x1010 : 0x7610), __byte_perm(tp, 0, 0x1010), __byte_perm(tp, 0, 0x1032), __byte_perm(nt, tp, 0x7610));
        E4[(tid < 32 ? 159 : 209 - 32) + tid] = make_uint2(pack2(ua.x + ub.x, ua.y + ub.y), pack2(ua.z + ub.z, ua.w + ub.w - (tid == 31 ? s2 : 0.f)));
        if (tid == 63) E4[241] = make_uint2(__float_as_uint(s2) >> 16, 0u);
    }
    CSK(5);
    SPAN(0, 3);
}

#define CV_SLEEP 40
#define CV_LD "ld.relaxed.gpu.global"
#define CV_NL 1
#define CV_D2 3
#define CV_PDH 12
#define CV_PDF 4
#define CV_HAND 7
constexpr int CV_CPB = 5;
constexpr int CV_THREADS = 512;
constexpr int UPADF = 128;
constexpr int ULEN = UPADF + SEQ;
constexpr int XLEN = XCP;
constexpr int BX_5 = 0, BX_3 = 3264, BX_9 = 6528, BX_7 = 8960, BX_LEN = 11392;
constexpr int CV_SM_U = 0;
constexpr int CV_SM_T = CV_CPB * ULEN * 2;
constexpr int CV_SM_B = CV_SM_T + CV_CPB * TAPB;
constexpr int CV_SM_X = CV_SM_B + CV_CPB * BX_LEN;
constexpr int CV_SM_Y = (CV_SM_X + CV_CPB * XLEN * 2 + 127) & ~127;
constexpr int CV_SM_CNT = CV_SM_Y + CV_CPB * 8192;
constexpr int CV_SM_O = CV_SM_CNT + 128;
constexpr int CV_SMEM = CV_SM_O + 20480 + CST_EXTRA;
static_assert(ULEN % 128 == 0 && CV_SM_B % 128 == 0 && CV_SM_CNT % 128 == 0, "layout");

__device__ __forceinline__ uint32_t sub2(uint32_t x, uint32_t m) {
    const __nv_bfloat162 d = __hsub2(*reinterpret_cast<const __nv_bfloat162*>(&x), *reinterpret_cast<const __nv_bfloat162*>(&m));
    return *reinterpret_cast<const uint32_t*>(&d);
}
__device__ __forceinline__ uint32_t add2(uint32_t x, uint32_t y) {
    const __nv_bfloat162 d = __hadd2_rn(*reinterpret_cast<const __nv_bfloat162*>(&x), *reinterpret_cast<const __nv_bfloat162*>(&y));
    return *reinterpret_cast<const uint32_t*>(&d);
}
__device__ __forceinline__ void wgmma_fence() { asm volatile("wgmma.fence.sync.aligned;" ::: "memory"); }
__device__ __forceinline__ void wgmma_commit() { asm volatile("wgmma.commit_group.sync.aligned;" ::: "memory"); }
template <int N> __device__ __forceinline__ void wgmma_wait() { asm volatile("wgmma.wait_group.sync.aligned %0;" ::"n"(N) : "memory"); }
__device__ __forceinline__ uint64_t make_desc(uint32_t addr, uint32_t lbo, uint32_t sbo, uint32_t mode) {
    return (uint64_t)((addr & 0x3FFFF) >> 4) | ((uint64_t)(lbo >> 4) << 16) | ((uint64_t)(sbo >> 4) << 32) | ((uint64_t)mode << 62);
}
__device__ __forceinline__ void wgmma_rs128(float (&d)[64], uint2 hi, uint2 lo, uint64_t db, int acc) {
    asm volatile("{\n.reg .pred p;\nsetp.ne.b32 p, %69, 0;\nwgmma.mma_async.sync.aligned.m64n128k16.f32.bf16.bf16 {%0,%1,%2,%3,%4,%5,%6,%7,%8,%9,%10,%11,%12,%13,%14,%15,%16,%17,%18,%19,%20,%21,%22,%23,%24,%25,%26,%27,%28,%29,%30,%31,%32,%33,%34,%35,%36,%37,%38,%39,%40,%41,%42,%43,%44,%45,%46,%47,%48,%49,%50,%51,%52,%53,%54,%55,%56,%57,%58,%59,%60,%61,%62,%63}, {%64,%65,%66,%67}, %68, p, 1, 1, 0;\n}"
                 : "+f"(d[0]), "+f"(d[1]), "+f"(d[2]), "+f"(d[3]), "+f"(d[4]), "+f"(d[5]), "+f"(d[6]), "+f"(d[7]), "+f"(d[8]), "+f"(d[9]), "+f"(d[10]), "+f"(d[11]), "+f"(d[12]), "+f"(d[13]), "+f"(d[14]), "+f"(d[15]), "+f"(d[16]), "+f"(d[17]), "+f"(d[18]), "+f"(d[19]), "+f"(d[20]), "+f"(d[21]), "+f"(d[22]), "+f"(d[23]), "+f"(d[24]), "+f"(d[25]), "+f"(d[26]), "+f"(d[27]), "+f"(d[28]), "+f"(d[29]), "+f"(d[30]), "+f"(d[31]), "+f"(d[32]), "+f"(d[33]), "+f"(d[34]), "+f"(d[35]), "+f"(d[36]), "+f"(d[37]), "+f"(d[38]), "+f"(d[39]), "+f"(d[40]), "+f"(d[41]), "+f"(d[42]), "+f"(d[43]), "+f"(d[44]), "+f"(d[45]), "+f"(d[46]), "+f"(d[47]), "+f"(d[48]), "+f"(d[49]), "+f"(d[50]), "+f"(d[51]), "+f"(d[52]), "+f"(d[53]), "+f"(d[54]), "+f"(d[55]), "+f"(d[56]), "+f"(d[57]), "+f"(d[58]), "+f"(d[59]), "+f"(d[60]), "+f"(d[61]), "+f"(d[62]), "+f"(d[63])
                 : "r"(hi.x), "r"(hi.y), "r"(lo.x), "r"(lo.y), "l"(db), "r"(acc));
}
template <int V> struct Int { __device__ constexpr operator int() const { return V; } };
__device__ __forceinline__ void sts4(uint32_t a, const uint32_t* v) { asm volatile("st.shared.v4.u32 [%0], {%1,%2,%3,%4};" ::"r"(a), "r"(v[0]), "r"(v[1]), "r"(v[2]), "r"(v[3]) : "memory"); }
__device__ __forceinline__ uint32_t lds1(uint32_t a) { uint32_t v; asm volatile("ld.shared.u32 %0, [%1];" : "=r"(v) : "r"(a) : "memory"); return v; }
__device__ __forceinline__ uint32_t lds1v(uint32_t a) { uint32_t v; asm volatile("ld.volatile.shared.u32 %0, [%1];" : "=r"(v) : "r"(a) : "memory"); return v; }
__device__ __forceinline__ uint4 lds4(uint32_t a) { uint4 v; asm volatile("ld.shared.v4.u32 {%0,%1,%2,%3}, [%4];" : "=r"(v.x), "=r"(v.y), "=r"(v.z), "=r"(v.w) : "r"(a) : "memory"); return v; }
__device__ __forceinline__ uint4 ldx(uint32_t a) {
    uint4 v;
    asm volatile("ld.shared.v2.u32 {%0,%1}, [%4];\nld.shared.v2.u32 {%2,%3}, [%4+128];" : "=r"(v.x), "=r"(v.y), "=r"(v.z), "=r"(v.w) : "r"(a) : "memory");
    return v;
}
__device__ __forceinline__ void cv_store(unsigned char* p, uint4 x, uint4 y) {
    asm volatile("st.relaxed.gpu.global.v2.u32 [%0], {%1,%2};" ::"l"(p), "r"(add2(x.x, __byte_perm(y.x, y.y, 0x5410))), "r"(add2(x.y, __byte_perm(y.z, y.w, 0x5410))) : "memory");
    asm volatile("st.relaxed.gpu.global.v2.u32 [%0], {%1,%2};" ::"l"(p + 128), "r"(add2(x.z, __byte_perm(y.x, y.y, 0x7632))), "r"(add2(x.w, __byte_perm(y.z, y.w, 0x7632))) : "memory");
}
__device__ __forceinline__ int usw(int ch) { return ch ^ ((ch >> 3) & 1); }
__global__ void __launch_bounds__(CV_THREADS, 1) conv_kernel(int layer, const uint4* __restrict__ piv, const float4* __restrict__ sum, const bf16* __restrict__ x1T,
                                                             bf16* __restrict__ dst, const uint4* __restrict__ tap, const __grid_constant__ CUtensorMap tmOut) {
    extern __shared__ __align__(1024) unsigned char sm[];
    SPAN(3 + 4 * layer, 0);
    bf16* Us = reinterpret_cast<bf16*>(sm + CV_SM_U);
    bf16* Xs = reinterpret_cast<bf16*>(sm + CV_SM_X);
#define CV_IDX int tid; asm volatile("mov.u32 %0, %tid.x;" : "=r"(tid)); const int lane = tid & 31, warp = __shfl_sync(~0u, tid >> 5, 0);
    const int d0 = blockIdx.x * CV_CPB, tile = blockIdx.x; (void)tile;
    const uint32_t cnt = smem_u32(sm + CV_SM_CNT);
    struct Lc { uint32_t a4, a8, uc, ud, y, e4, en, sp, ss; int go; };
    auto lane_consts = [&](int lane, int c) {
        const int mat = lane >> 3, r = lane & 7, g = lane >> 2, ti = lane & 3, e = g - 2 * ti;
        const int j2 = 13 + (r ^ 1) + 8 * (mat >> 1), j3 = j2 + 2, i0 = 8 * (mat & 1);
        const uint32_t sb = smem_u32(sm), oc = sb + usw(16 * (mat >> 1) + 2 * r + (mat & 1)) * 16;
        const Lc l = {sb + CV_SM_B + c * BX_LEN + ((j2 & 1) ? BX_3 + (4 * j2 + i0 + 84) * 2 : BX_5 + (4 * j2 + i0 + 80) * 2),
                      sb + CV_SM_B + c * BX_LEN + ((j3 & 1) ? BX_7 : BX_9) + (8 * j3 + i0 + 136) * 2,
                      oc + CV_SM_U + (c * ULEN + UPADF) * 2, sb + CV_SM_U + (c * ULEN + UPADF) * 2 + usw(16 * mat + 2 * r + 2) * 16, oc + CV_SM_Y + c * 8192,
                      sb + CV_SM_T + c * TAPB + TAPE + (307 + 2 * g - ti) * 4, sb + CV_SM_T + c * TAPB + (528 + e) * 4,
                      e == -5 ? 0x4410u : e == -4 ? 0x1044u : 0x4444u, e == 3 ? 0x4410u : e == 4 ? 0x1044u : 0x4444u,
                      c * XCP * 2 + (lane >> 4) * 256 + (lane & 15) * 8};
        asm volatile("st.shared.u32 [%0], %1;" ::"r"(sb + CV_SM_CNT + 120), "r"(l.y ^ l.a4 ^ l.a8 ^ l.uc ^ l.ud ^ l.e4 ^ l.en ^ l.sp ^ l.ss ^ l.go) : "memory");
        return l;
    };
    unsigned char* const dq = reinterpret_cast<unsigned char*>(dst + (size_t)d0 * XCP);
    auto far = [&](auto T0_, const auto& seq, const Lc& lc, int c, int lane, const uint2 (&f)[20], uint32_t kk) {
        constexpr int T0 = T0_, T1 = T0 + 6, TC = T0 > 7 ? T0 : 7, NS = sizeof(seq) / sizeof(seq[0]), PD = T0 > 7 ? CV_PDH : CV_PDF;
        uint32_t bq[28], yw[4], yz[4], P, S;
        uint4 xv, yv;
        asm("prmt.b32 %0, %1, 0, %2;" : "=r"(P) : "r"(kk), "r"(lc.sp));
        asm("prmt.b32 %0, %1, 0, %2;" : "=r"(S) : "r"(kk), "r"(lc.ss));
#pragma unroll
        for (int k = 0; 2 * k < T1 - TC + 4; k++) ldsm_x4(bq + 4 * k, lc.uc + (TC - 8) * 256 + 512 * k);
#pragma unroll
        for (int k = 0; 4 * k < T1 - TC; k++) ldsm_x4(bq + 20 + 4 * k, lc.ud + (TC - 8) * 256 + 1024 * k);
        CST(3);
        mbar_wait(cnt + 8 * c, 0);
        mbar_wait(cnt + 40, 0);
        CST(4);
        float acc[6][4] = {};
        uint32_t a[PD + 1][4];
#pragma unroll
        for (int i = -PD; i < NS + 3; i++) {
            if (i + PD < NS) ldsm_x4_t(a[(i + PD) % (PD + 1)], seq[i + PD] < 32 ? lc.a4 + (seq[i + PD] - 2) * 128 : lc.a8 + (seq[i + PD] - 34) * 256);
            if (i < 0) continue;
#pragma unroll
            for (int T = T0; T < T1; T++) {
                if (i >= NS) break;
                const int ee = seq[i] < 32 ? 2 * T - 6 - seq[i] : T + 35 - seq[i];
                if (i == 0 && T >= TC) mma_bf16(acc[T - T0], P, 0u, S, P, bq[2 * (T - TC)], bq[2 * (T - TC) + 1]);
                if (i == 1 && T >= TC) mma_bf16_k8(acc[T - T0], 0u, S, bq[20 + T - TC]);
                if (i == (T >= TC ? 2 : 0)) mma_bf16(acc[T - T0], f[19].x, 0u, f[19].y, f[19].x, bq[2 * (T - TC + 4)], bq[2 * (T - TC + 4) + 1]);
                if (seq[i] < 32 ? ee >= 0 && ee <= 9 : ee >= 10) mma_bf16(acc[T - T0], a[i % (PD + 1)][0], a[i % (PD + 1)][1], a[i % (PD + 1)][2], a[i % (PD + 1)][3], f[ee].x, f[ee].y);
            }
#pragma unroll
            for (int k = 0; k < 3; k++) {
                const int o = 256 * T0 + 512 * k;
                auto at = [&](int d) { return i - d >= 0 && i - d < NS && seq[i - d < 0 ? 0 : i - d < NS ? i - d : 0] == 2 * T0 + 4 * k - 4; };
                if (at(CV_D2)) {
                    cv_store(dq + lc.go + o, xv, yv);
                    if (layer > 19 - 2 * k) __trap();
                }
                if (at(-2)) { ldsm_x4_t(yw, lc.y + o); ldsm_x4_t(yz, lc.y + 3584 + o); }
                if (at(1)) {
#pragma unroll
                    for (int q = 0; q < 4; q++) yw[q] = add2(add2(yw[q], yz[q]), pack2(acc[2 * k + (q >> 1)][2 * (q & 1)], acc[2 * k + (q >> 1)][2 * (q & 1) + 1]));
                    stsm_x4_t(lc.y + o, yw[0], yw[1], yw[2], yw[3]);
                    xv = ldx(smem_u32(Xs) + lc.go + o);
                    __syncwarp();
                    yv = lds4(smem_u32(sm + CV_SM_Y) + c * 8192 + o + usw(lane) * 16);
                    if (layer > 20 - 2 * k) __trap();
                    if (k == 2) CST(6);
                }
            }
        }
    };
    TSTAMP1X(9, 256);
    if (threadIdx.x >= 256) {
        if (threadIdx.x < 288 && elect()) {
            mbar_init(cnt + 48, 1);
            asm volatile("fence.mbarrier_init.release.cluster;" ::: "memory");
            bulk_load(smem_u32(sm + CV_SM_T), tap + d0 * (TAPB / 16), CV_CPB * TAPB, cnt + 48);
            mbar_expect_tx(cnt + 48, CV_CPB * TAPB);
        }
        CV_IDX
        const int wgu = (warp >> 2) & 1, g = lane >> 2, ti = lane & 3;
        CST(1);
        if (warp > 8 && elect()) {
            if (warp < 15) mbar_init(cnt + 8 * (warp - 9), warp == 14 ? 8 : 4);
            else if (layer) prefetch_tmap(&tmOut);
        }
        if (warp < 13 && lane < 17 - (warp == 12)) {
            const int off = warp == 12 ? CV_SM_U : CV_SM_B + (warp == 11 ? BX_7 : (warp - 8) * BX_3), str = warp == 12 ? ULEN * 2 : BX_LEN;
#pragma unroll
            for (int c = 0; c < CV_CPB; c++) *reinterpret_cast<uint4*>(sm + off + c * str + 16 * lane) = make_uint4(0, 0, 0, 0);
        }
        fence_async_smem();
        asm volatile("bar.arrive 3, 512;" ::: "memory");
        asm volatile("bar.sync 1, 256;" ::: "memory");
        TSTAMP1X(10, 256);
        asm volatile("setmaxnreg.inc.sync.aligned.u32 168;");
        const uint32_t Tc = smem_u32(sm + CV_SM_T) + (16 + 128 * (warp & 2) + 8 * (warp & 1) + g - 2 * ti) * 4;
        uint2 fa[8][2], fn[8][2];
        auto near_taps = [&](uint2 (&f)[8][2], int c) {
#pragma unroll
            for (int m = 0; m < 16; m++) f[m >> 1][m & 1] = make_uint2(lds1v(Tc + c * TAPB + 64 * (m >> 1) - 32 * (m & 1)), lds1v(Tc + c * TAPB + 64 * (m >> 1) - 32 * (m & 1) + 512));
        };
        CST(6);
        mbar_wait(cnt + 48, 0);
        TSTAMP1X(11, 256); CST(5);
        near_taps(fa, 3 * wgu);
        near_taps(fn, 2 - wgu);
        const int hc = wgu ? warp & 3 : 4;
        const Lc lc = lane_consts(lane, hc);
        TSTAMP1X(12, 256); CST(0);
        uint32_t ya = smem_u32(sm + CV_SM_Y) + wgu * 8192 + (warp & 2) * 2048 + usw(2 * lane + (warp & 1)) * 16;
        uint64_t db = make_desc(smem_u32(Us + wgu * ULEN + UPADF), 16, 256, 3);
        if (wgu) { asm volatile("bar.sync 6, 384;" ::: "memory"); fence_async_smem(); }
        int c = wgu;
        auto chain = [&](const uint2 (&f)[8][2], auto&& meanwhile) {
            float acc[64];
            asm volatile("bar.sync %0, %1;" ::"r"(c ? 4 + wgu : 2), "r"(c ? 256 : 384) : "memory");
            TSTAMPC(1 + 3 * c);
            if (c < 2) CST(7);
            if (c == 0) fence_async_smem();
            wgmma_fence();
#pragma unroll
            for (int m = 0; m < 8; m++) {
                wgmma_rs128(acc, f[m][0], f[m][1], db - (uint64_t)(2 * m), m);
                if (m == CV_HAND && c < 4) asm volatile("bar.arrive %0, 256;" ::"r"(5 - wgu) : "memory");
            }
            wgmma_commit();
            asm volatile("griddepcontrol.launch_dependents;" ::: "memory");
            TSTAMPC(2 + 3 * c); CST(13 + (c >> 1));
            meanwhile();
            wgmma_wait<0>();
            TSTAMPC(3 + 3 * c); CST(10 + (c >> 1));
            uint32_t w[16];
#pragma unroll
            for (int j = 0; j < 16; j++) w[j] = j ? pack2(acc[4 * j] + acc[4 * j - 2], acc[4 * j + 1] + acc[4 * j - 1]) : pack2(acc[0], acc[1]);
#pragma unroll
            for (int j = 0; j < 16; j += 4) stsm_x4_t(ya + 256 * j, w[j], w[j + 1], w[j + 2], w[j + 3]);
            __syncwarp();
            if (lane == 0) mbar_arrive(cnt + 8 * c);
            c += 2; ya += 16384; db += ULEN / 4;
        };
        const uint32_t e4 = lc.e4, e8 = e4 + 428 - 4 * g;
        uint2 fl[4];
        uint32_t kk;
#pragma unroll 1
        for (;;) {
            if (c != 1) chain(fa, [&] {
                if (c == 3 || warp + c == 12) {
#pragma unroll
                    for (int k = 0; k < 19; k++) (k < 16 ? fn[(k >> 1) & 7][k & 1] : fl[k & 3]) = make_uint2(lds1(k < 10 ? e4 + 32 * k + 16 : e8 + 32 * k - 304), lds1(k < 10 ? e4 + 32 * k : e8 + 32 * k - 320));
                    fl[3] = make_uint2(lds1(lc.en), lds1(lc.en - 32));
                    kk = lds1(smem_u32(sm + CV_SM_T) + TAPB * hc + TAPE + 1672);
                }
            });
            if (c > 4) break;
            if (c == 2) { asm volatile("bar.sync 7, 384;" ::: "memory"); fence_async_smem(); }
            chain(fn, [&] { if (c == 2) near_taps(fa, 4); });
        }
        TSTAMP1X(6, 256); CST(2);
        if (wgu || warp == 8) {
            constexpr int seq[29] = {5, 6, 32, 7, 33, 8, 34, 9, 35, 10, 36, 11, 12, 13, 14, 15, 16, 17, 37, 18, 38, 19, 20, 21, 39, 22, 40, 23, 24};
            uint2 f[20];
#pragma unroll
            for (int k = 0; k < 20; k++) f[k] = k < 16 ? fn[(k >> 1) & 7][k & 1] : fl[k & 3];
            far(Int<10>(), seq, lc, hc, lane, f, kk);
        }
    } else {
        asm volatile("setmaxnreg.dec.sync.aligned.u32 88;");
        CV_IDX
        CST(5);
        const uint4* ppv = piv + tid;
        const float4* psv = sum + tid;
        const uint2* pxv = reinterpret_cast<const uint2*>(x1T + (size_t)d0 * XCP) + (tid >> 4) * 32 + (tid & 15);
        asm volatile("st.shared.u64 [%0], %1;" ::"r"(smem_u32(sm + CV_SM_O) + tid * 16), "l"((uint64_t)ppv ^ (uint64_t)psv ^ (uint64_t)pxv) : "memory");
        const int tc = (0x04302100 >> (4 * warp)) & 7;
        const Lc lc = lane_consts(lane, tc);
        pdl_sync();
        SPAN(3 + 4 * layer, 1);
        TSTAMP(0); CST(0);
        if (tid == 0) TSTAMPC(0);
        if (threadIdx.x == 0) { GSTAMP(g_tim, 15); }
        float4 sv[4];
        uint4 pv;
#pragma unroll
        for (int k = 0; k < 4; k++)
            asm volatile(CV_LD ".v4.f32 {%0,%1,%2,%3}, [%4];" : "=f"(sv[k].x), "=f"(sv[k].y), "=f"(sv[k].z), "=f"(sv[k].w) : "l"(psv + 256 * k) : "memory");
        asm volatile(CV_LD ".v4.u32 {%0,%1,%2,%3}, [%4];" : "=r"(pv.x), "=r"(pv.y), "=r"(pv.z), "=r"(pv.w) : "l"(ppv) : "memory");
        uint2 xe[CV_CPB], xo[CV_CPB];
#pragma unroll
        for (int c = 0; c < CV_NL; c++) {
            asm volatile(CV_LD ".v2.u32 {%0,%1}, [%2];" : "=r"(xe[c].x), "=r"(xe[c].y) : "l"(pxv + c * (XCP / 4)) : "memory");
            asm volatile(CV_LD ".v2.u32 {%0,%1}, [%2];" : "=r"(xo[c].x), "=r"(xo[c].y) : "l"(pxv + c * (XCP / 4) + 16) : "memory");
        }
#define CV_XD 300
#define CV_XW 0
        if (warp == CV_XW) {
            if (elect()) {
                const uint32_t c0 = clock();
                mbar_init(cnt + 56, 1);
                asm volatile("fence.mbarrier_init.release.cluster;" ::: "memory");
                mbar_expect_tx(cnt + 56, CV_CPB * 4096);
                while (clock() - c0 < CV_XD) ;
#pragma unroll
                for (int c = CV_NL; c < CV_CPB + CV_NL; c++) bulk_load(smem_u32(Xs + (c % CV_CPB) * XLEN), x1T + (size_t)(d0 + c % CV_CPB) * XCP, 4096, cnt + 56);
            }
            __syncwarp();
            CST(15);
        }
        constexpr float idm = 1.0f / DM;
        uint32_t mw[4];
        float rs[8];
#pragma unroll
        for (int k = 0; k < 4; k++) {
            const uint32_t pw = k == 0 ? pv.x : k == 1 ? pv.y : k == 2 ? pv.z : pv.w;
            mw[k] = pack2(fmaf(sv[k].x, idm, __uint_as_float(pw << 16)), fmaf(sv[k].z, idm, __uint_as_float(pw & 0xffff0000u)));
            uint32_t vr;
            asm("cvt.rn.relu.bf16x2.f32 %0, %1, %2;" : "=r"(vr) : "f"(fmaf(sv[k].z * -idm, sv[k].z, sv[k].w) * idm), "f"(fmaf(sv[k].x * -idm, sv[k].x, sv[k].y) * idm));
            const uint32_t ve = pack2(__uint_as_float(vr << 16) + 1e-5f, __uint_as_float(vr & 0xffff0000u) + 1e-5f);
            const uint32_t sd = pack2(sqrt_apx(__uint_as_float(ve << 16)), sqrt_apx(__uint_as_float(ve & 0xffff0000u)));
            rs[2 * k] = rcp_apx(__uint_as_float(sd << 16)); rs[2 * k + 1] = rcp_apx(__uint_as_float(sd & 0xffff0000u));
        }
        if (rs[0] != 123.f) TSTAMP(13);
        const uint32_t ua = smem_u32(Us) + usw(tid + UPADF / 8) * 16;
        uint32_t uw[CV_CPB][4];
#pragma unroll
        for (int c = 0; c < CV_CPB; c++) {
            if (c == CV_NL) {
                if (warp == CV_XW) { mbar_wait(cnt + 56, 0); CST(7); }
                asm volatile("bar.sync 10, 256;" ::: "memory");
            }
            if (c == 1 || c == 2) {
#pragma unroll
                for (int k = c; k < (c == 1 ? 2 : CV_CPB); k++) {
 const uint4 v = ldx(smem_u32(Xs + k * XLEN) + (tid >> 4) * 256 + (tid & 15) * 8); xe[k] = make_uint2(v.x, v.y); xo[k] = make_uint2(v.z, v.w); }
            }
            const uint32_t e0 = sub2(xe[c].x, mw[0]), e1 = sub2(xe[c].y, mw[1]), o0 = sub2(xo[c].x, mw[2]), o1 = sub2(xo[c].y, mw[3]);
            uw[c][0] = pack2(__uint_as_float(e0 << 16) * rs[0], __uint_as_float(o0 << 16) * rs[4]); uw[c][1] = pack2(__uint_as_float(e0 & 0xffff0000u) * rs[1], __uint_as_float(o0 & 0xffff0000u) * rs[5]);
            uw[c][2] = pack2(__uint_as_float(e1 << 16) * rs[2], __uint_as_float(o1 << 16) * rs[6]); uw[c][3] = pack2(__uint_as_float(e1 & 0xffff0000u) * rs[3], __uint_as_float(o1 & 0xffff0000u) * rs[7]);
            asm volatile("st.shared.v4.u32 [%0], {%1,%2,%3,%4};" ::"r"(ua + c * ULEN * 2), "r"(uw[c][0]), "r"(uw[c][1]), "r"(uw[c][2]), "r"(uw[c][3]) : "memory");
            if (c < 2) {
                asm volatile("bar.arrive %0, 384;" ::"r"(2 + 4 * c) : "memory");
                if (layer > 29 - c) __trap();
                CST(11 + c);
            }
        }
        asm volatile("bar.arrive 7, 384;" ::: "memory");
        asm volatile("bar.sync 3, 512;" ::: "memory");
        TSTAMP(1); CST(1);
        {
            auto box = [&](auto c0, auto c1, int chunk, int cb, bool full) {
                const uint32_t ea = smem_u32(Us + cb * ULEN) + usw(chunk + UPADF / 8 + (lane ? 1 : -1)) * 16, bx = smem_u32(sm + CV_SM_B + cb * BX_LEN) + chunk * 16;
                uint32_t lo[CV_CPB][4], hi[CV_CPB][2];
#pragma unroll
                for (int c = c0; c < c1; c++) {
                    lo[c][0] = 0;
#pragma unroll
                    for (int k = 1; k < 4; k++) lo[c][k] = __shfl_up_sync(~0u, uw[c][k], 1);
#pragma unroll
                    for (int k = 0; k < 2; k++) hi[c][k] = __shfl_down_sync(~0u, uw[c][k], 1);
                }
#pragma unroll
                for (int c = c0; c < c1; c++)
                    asm volatile("{\n.reg .pred p, q;\nsetp.eq.s32 p, %7, 0;\nsetp.eq.s32 q, %7, 31;\n@p ld.shared.v4.u32 {%0,%1,%2,%3}, [%6];\n@q ld.shared.v2.u32 {%4,%5}, [%6];\n}"
                                 : "+r"(lo[c][0]), "+r"(lo[c][1]), "+r"(lo[c][2]), "+r"(lo[c][3]), "+r"(hi[c][0]), "+r"(hi[c][1]) : "r"(ea + c * ULEN * 2), "r"(lane) : "memory");
#pragma unroll
                for (int c = c0; c < c1; c++) {
                    const uint32_t e[9] = {lo[c][1], lo[c][2], lo[c][3], uw[c][0], uw[c][1], uw[c][2], uw[c][3], hi[c][0], hi[c][1]};
                    uint32_t o[8], p[8], t[7], b3[5], b5[7];
#pragma unroll
                    for (int i = 0; i < 8; i++) { o[i] = __byte_perm(e[i], e[i + 1], 0x5432); p[i] = add2(e[i], o[i]); }
#pragma unroll
                    for (int i = 0; i < 5; i++) b3[i] = add2(o[i], p[i + 1]);
                    sts4(bx + c * BX_LEN + BX_3 + 160, b3);
#pragma unroll
                    for (int i = 1; i < 7; i++) { t[i] = add2(p[i], p[i + 1]); b5[i] = add2(t[i], e[i + 2]); }
                    sts4(bx + c * BX_LEN + BX_5 + 160, b5 + 2);
                    if (full) {
#pragma unroll
                        for (int i = 1; i < 5; i++) { b3[i] = add2(b3[i], t[i + 2]); t[i] = add2(t[i], b5[i + 2]); }
                        sts4(bx + c * BX_LEN + BX_7 + 272, b3 + 1);
                        sts4(bx + c * BX_LEN + BX_9 + 272, t + 1);
                    }
                }
            };
            auto reload = [&](int c, uint32_t a) { const uint4 v = lds4(a); uw[c][0] = v.x; uw[c][1] = v.y; uw[c][2] = v.z; uw[c][3] = v.w; };
            if (warp >= 6) {
#pragma unroll
                for (int c = 0; c < 3; c++) reload(c, ua - 1024 + (c + 2) * ULEN * 2);
            }
            if (warp >= 4) {
#pragma unroll
                for (int c = 3; c < 5; c++) reload(c, ua - 2048 + c * ULEN * 2);
            }
            box(Int<0>(), Int<3>(), warp < 6 ? tid : tid - 64, warp < 6 ? 0 : 2, warp < 4);
            if (warp >= 4) box(Int<3>(), Int<5>(), tid - 128, 0, true);
            else if (tid >= 128 - CV_CPB) {
                const int c = 127 - tid;
                const uint2 v = *reinterpret_cast<const uint2*>(Us + c * ULEN + UPADF);
                const float s1 = __uint_as_float(v.x << 16), s2 = s1 + __uint_as_float(v.x & 0xffff0000u), s3 = s2 + __uint_as_float(v.y << 16), s4 = s3 + __uint_as_float(v.y & 0xffff0000u);
                unsigned char* bc = sm + CV_SM_B + c * BX_LEN;
                *reinterpret_cast<uint32_t*>(bc + BX_5 + 156) = pack2(s1, s2);
                *reinterpret_cast<uint2*>(bc + BX_7 + 264) = make_uint2(v.x << 16, pack2(s2, s3));
                *reinterpret_cast<uint2*>(bc + BX_9 + 264) = make_uint2(pack2(s1, s2), pack2(s3, s4));
            }
        }
        __syncwarp();
        if (lane == 0) mbar_arrive(cnt + 40);
        TSTAMP(2); CST(2);
        if (layer && blockIdx.x == 0 && tid == 224) g_epoch = ld_epoch();
        __syncwarp();
        if ((0x6e >> warp) & 1) {
            constexpr int seq[16] = {0, 1, 2, 3, 4, 5, 6, 32, 7, 8, 9, 33, 10, 34, 11, 12};
            uint2 f[20];
            mbar_wait(cnt, 0);
            const uint32_t e8 = lc.e4 + 428 - (lane & 28);
#pragma unroll
            for (int k = 0; k < 13; k++) f[k] = make_uint2(lds1(k < 10 ? lc.e4 + 32 * k + 16 : e8 + 32 * k - 304), lds1(k < 10 ? lc.e4 + 32 * k : e8 + 32 * k - 320));
            f[19] = make_uint2(lds1(lc.en), lds1(lc.en - 32));
            far(Int<4>(), seq, lc, tc, lane, f, lds1(smem_u32(sm + CV_SM_T) + TAPB * tc + TAPE + 1672));
        }
    }
    {
        CV_IDX
        if ((0xc91 >> warp) & 1) {
            const int c = __popc(0xc91 & ((1 << warp) - 1));
            uint4 xv[2], yv[2];
#pragma unroll
            for (int k = 0; k < 2; k++) xv[k] = ldx(smem_u32(Xs + c * XLEN) + 512 * k + (lane >> 4) * 256 + (lane & 15) * 8);
            const uint32_t u0 = lds1(smem_u32(Us + c * ULEN) + (lane == 31 ? UPADF * 2 : 0));
            mbar_wait(cnt + 8 * c, 0);
#pragma unroll
            for (int k = 0; k < 2; k++) yv[k] = lds4(smem_u32(sm + CV_SM_Y) + c * 8192 + 512 * k + usw(lane) * 16);
            const uint4 yz = lds4(smem_u32(sm + CV_SM_Y) + c * 8192 + 4096 + usw(lane) * 16);
            const float kk = __uint_as_float(lds1(smem_u32(sm + CV_SM_T) + TAPB * c + TAPE + 1272) << 16);
            yv[1].x = add2(yv[1].x, yz.x); yv[1].y = add2(yv[1].y, yz.y); yv[1].z = add2(yv[1].z, yz.z);
            yv[1].w = pack2(fmaf(kk, __uint_as_float(u0 << 16), __uint_as_float(yv[1].w << 16) + __uint_as_float(yz.w << 16)),
                            fmaf(kk, __uint_as_float(u0 << 16) + __uint_as_float(u0 & 0xffff0000u), __uint_as_float(yv[1].w & 0xffff0000u) + __uint_as_float(yz.w & 0xffff0000u)));
#pragma unroll
            for (int k = 0; k < 2; k++) cv_store(dq + c * XCP * 2 + (lane >> 4) * 256 + (lane & 15) * 8 + 512 * k, xv[k], yv[k]);
        }
        TSTAMP(4); CST(8);
        if (layer == 1) {
            const int rb = (blockIdx.x >> 3) + (warp & 8) * 2, cg = blockIdx.x & 7, ch = (tid >> 3) & 31;
            const bf16* src = dst + (size_t)(cg * 80 + ch) * XCP + rb * 64 + (tid & 7) * 8;
            uint32_t v[3][4];
            __syncthreads();
            if (warp & 8) { const uint32_t c0 = clock(); while (clock() - c0 < 300) ; }
            uint32_t todo = (warp & 4) ? 3 : 7;
#pragma unroll 1
            for (int it = 0; it < SPIN_MAX; it++) {
#pragma unroll
                for (int k = 0; k < 3; k++)
                    if (todo >> k & 1)
                        asm volatile("ld.relaxed.gpu.global.v4.u32 {%0,%1,%2,%3}, [%4];" : "=r"(v[k][0]), "=r"(v[k][1]), "=r"(v[k][2]), "=r"(v[k][3]) : "l"(src + k * (32 * XCP)) : "memory");
#pragma unroll
                for (int k = 0; k < 3; k++)
                    if ((todo >> k & 1) && v[k][0] != ~0u && v[k][1] != ~0u && v[k][2] != ~0u && v[k][3] != ~0u) {
                        *reinterpret_cast<uint4*>(sm + (32 * k + ch) * 272 + ((tid & 7) + (warp & 8)) * 16) = make_uint4(v[k][0], v[k][1], v[k][2], v[k][3]);
                        todo ^= 1u << k;
                    }
                if (!todo) break;
                __nanosleep(CV_SLEEP);
            }
            __syncwarp();
            asm volatile("bar.sync %0, 256;" ::"r"(8 + (warp >> 3)) : "memory");
            uint32_t w[12];
#pragma unroll
            for (int k = 0; k < 3; k++) ldsm_x4(&w[4 * k], smem_u32(sm) + min(32 * k + lane, 79) * 272 + warp * 16);
            const uint32_t ot = smem_u32(sm + CV_SM_O) + warp * 1280, oa = ot + (lane & 7) * 160 + (lane >> 3) * 16;
            stsm_x4_t(oa, w[0], w[1], w[2], w[3]);
            stsm_x4_t(oa + 64, w[4], w[5], w[6], w[7]);
            asm volatile("stmatrix.sync.aligned.m8n8.x2.trans.shared.b16 [%0], {%1,%2};" ::"r"(oa + 128), "r"(w[8]), "r"(w[9]) : "memory");
            fence_async_smem();
            __syncwarp();
            if (lane == 0) {
                asm volatile("cp.async.bulk.tensor.3d.global.shared::cta.bulk_group [%0, {%1, %2, %3}], [%4];" ::"l"(&tmOut), "r"(cg * 80), "r"((rb >> 1) * 64 + 8 * (warp & 7)), "r"(rb & 1), "r"(ot) : "memory");
                asm volatile("cp.async.bulk.commit_group;" ::: "memory");
                asm volatile("cp.async.bulk.wait_group.read 0;" ::: "memory");
            }
        }
    }
    TSTAMP(3); CST(9); CST_END;
    GSTAMP(g_tim, 14);
    SPAN(3 + 4 * layer, 3);
}

template <int TA, int TB>
__device__ __forceinline__ void wgmma_n240(float (&d)[120], uint64_t da, uint64_t db, int acc) {
    asm volatile("{\n.reg .pred p;\nsetp.ne.b32 p, %124, 0;\nwgmma.mma_async.sync.aligned.m64n240k16.f32.bf16.bf16 {%0,%1,%2,%3,%4,%5,%6,%7,%8,%9,%10,%11,%12,%13,%14,%15,%16,%17,%18,%19,%20,%21,%22,%23,%24,%25,%26,%27,%28,%29,%30,%31,%32,%33,%34,%35,%36,%37,%38,%39,%40,%41,%42,%43,%44,%45,%46,%47,%48,%49,%50,%51,%52,%53,%54,%55,%56,%57,%58,%59,%60,%61,%62,%63,%64,%65,%66,%67,%68,%69,%70,%71,%72,%73,%74,%75,%76,%77,%78,%79,%80,%81,%82,%83,%84,%85,%86,%87,%88,%89,%90,%91,%92,%93,%94,%95,%96,%97,%98,%99,%100,%101,%102,%103,%104,%105,%106,%107,%108,%109,%110,%111,%112,%113,%114,%115,%116,%117,%118,%119}, %120, %121, p, 1, 1, %122, %123;\n}"
                 : "+f"(d[0]), "+f"(d[1]), "+f"(d[2]), "+f"(d[3]), "+f"(d[4]), "+f"(d[5]), "+f"(d[6]), "+f"(d[7]), "+f"(d[8]), "+f"(d[9]), "+f"(d[10]), "+f"(d[11]), "+f"(d[12]), "+f"(d[13]), "+f"(d[14]), "+f"(d[15]), "+f"(d[16]), "+f"(d[17]), "+f"(d[18]), "+f"(d[19]), "+f"(d[20]), "+f"(d[21]), "+f"(d[22]), "+f"(d[23]), "+f"(d[24]), "+f"(d[25]), "+f"(d[26]), "+f"(d[27]), "+f"(d[28]), "+f"(d[29]), "+f"(d[30]), "+f"(d[31]), "+f"(d[32]), "+f"(d[33]), "+f"(d[34]), "+f"(d[35]), "+f"(d[36]), "+f"(d[37]), "+f"(d[38]), "+f"(d[39]), "+f"(d[40]), "+f"(d[41]), "+f"(d[42]), "+f"(d[43]), "+f"(d[44]), "+f"(d[45]), "+f"(d[46]), "+f"(d[47]), "+f"(d[48]), "+f"(d[49]), "+f"(d[50]), "+f"(d[51]), "+f"(d[52]), "+f"(d[53]), "+f"(d[54]), "+f"(d[55]), "+f"(d[56]), "+f"(d[57]), "+f"(d[58]), "+f"(d[59]), "+f"(d[60]), "+f"(d[61]), "+f"(d[62]), "+f"(d[63]), "+f"(d[64]), "+f"(d[65]), "+f"(d[66]), "+f"(d[67]), "+f"(d[68]), "+f"(d[69]), "+f"(d[70]), "+f"(d[71]), "+f"(d[72]), "+f"(d[73]), "+f"(d[74]), "+f"(d[75]), "+f"(d[76]), "+f"(d[77]), "+f"(d[78]), "+f"(d[79]), "+f"(d[80]), "+f"(d[81]), "+f"(d[82]), "+f"(d[83]), "+f"(d[84]), "+f"(d[85]), "+f"(d[86]), "+f"(d[87]), "+f"(d[88]), "+f"(d[89]), "+f"(d[90]), "+f"(d[91]), "+f"(d[92]), "+f"(d[93]), "+f"(d[94]), "+f"(d[95]), "+f"(d[96]), "+f"(d[97]), "+f"(d[98]), "+f"(d[99]), "+f"(d[100]), "+f"(d[101]), "+f"(d[102]), "+f"(d[103]), "+f"(d[104]), "+f"(d[105]), "+f"(d[106]), "+f"(d[107]), "+f"(d[108]), "+f"(d[109]), "+f"(d[110]), "+f"(d[111]), "+f"(d[112]), "+f"(d[113]), "+f"(d[114]), "+f"(d[115]), "+f"(d[116]), "+f"(d[117]), "+f"(d[118]), "+f"(d[119])
                 : "l"(da), "l"(db), "n"(TA), "n"(TB), "r"(acc));
}

__device__ __forceinline__ void wgmma_n80(float (&d)[40], uint64_t da, uint64_t db, int acc) {
    asm volatile("{\n.reg .pred p;\nsetp.ne.b32 p, %42, 0;\nwgmma.mma_async.sync.aligned.m64n80k16.f32.bf16.bf16 {%0,%1,%2,%3,%4,%5,%6,%7,%8,%9,%10,%11,%12,%13,%14,%15,%16,%17,%18,%19,%20,%21,%22,%23,%24,%25,%26,%27,%28,%29,%30,%31,%32,%33,%34,%35,%36,%37,%38,%39}, %40, %41, p, 1, 1, 0, 1;\n}"
                 : "+f"(d[0]), "+f"(d[1]), "+f"(d[2]), "+f"(d[3]), "+f"(d[4]), "+f"(d[5]), "+f"(d[6]), "+f"(d[7]), "+f"(d[8]), "+f"(d[9]), "+f"(d[10]), "+f"(d[11]), "+f"(d[12]), "+f"(d[13]), "+f"(d[14]), "+f"(d[15]), "+f"(d[16]), "+f"(d[17]), "+f"(d[18]), "+f"(d[19]), "+f"(d[20]), "+f"(d[21]), "+f"(d[22]), "+f"(d[23]), "+f"(d[24]), "+f"(d[25]), "+f"(d[26]), "+f"(d[27]), "+f"(d[28]), "+f"(d[29]), "+f"(d[30]), "+f"(d[31]), "+f"(d[32]), "+f"(d[33]), "+f"(d[34]), "+f"(d[35]), "+f"(d[36]), "+f"(d[37]), "+f"(d[38]), "+f"(d[39])
                 : "l"(da), "l"(db), "r"(acc));
}

constexpr int A1_THREADS = 384;
constexpr int A1_NST = 4;
#define A1_SKEW 8
constexpr int A1_STAGE = 16384 + WQ_STAGE;
constexpr int A1_KVP = 336;
constexpr int A1_SM_KV = 2 * A1_STAGE;
constexpr int A1_SM_END = A1_NST * A1_STAGE;
constexpr int A1_SM_BAR = A1_SM_END + 3072 + 3 * WOB + 64;
constexpr int A1_SM_RS = A1_SM_END + 512;
constexpr int A1_SM_W0 = A1_SM_END + 3072, A1_SM_W3 = A1_SM_END - 3 * WOB, A1_SM_A1 = 2 * WOB, A1_SM_A0 = A1_SM_A1 + 61440;
constexpr int A1_SM_XA = A1_SM_W0 + 2 * WOB, A1_SM_XB = A1_SM_XA + 2048;
constexpr int A1_SMEM = A1_SM_BAR + 512 + 7 * CST_EXTRA / 4;
static_assert(A1_SM_W3 >= A1_SM_KV + 144 * A1_KVP && A1_SM_W3 % 512 == 0 && A1_SM_A1 % 1024 == 0 && A1_SM_A0 <= A1_SM_KV && A1_SM_A0 + 61440 <= A1_SM_W3 && A1_SMEM <= 232448 && 11 * 4096 <= A1_STAGE, "layout");
__device__ __forceinline__ constexpr uint32_t wo_off(int h) { return h * WOB + (h < 3 ? A1_SM_W0 : h < 6 ? A1_SM_W3 - 3 * WOB : -6 * WOB); }
#define A1_FRED "red.relaxed.gpu.global.add.u32"
#define A1_FLD "ld.acquire.gpu.global.u32"
#define ST_SLEEP 20
#define ST_SLEEP0 300
#define WO_LATE bar_done
#define A1_P0 2
#define A1_PW (kb - 2)
#define A1_FSPIN SPIN_MAX
#define A1_FSLEEP 40
#define YT_LAYER 1
#define WOT 352
#define A1_WOAT 6

template <int L>
__device__ __forceinline__ void a1_mainloop(float (&acc)[120], uint32_t sbase, uint32_t bars, int wg, int tile) {
    constexpr int layer = L; (void)layer;
    const uint64_t da0 = L ? make_desc(sbase + wg * 8192, 8192, 1024, 1) : make_desc(sbase + wg * 8192, 16, 1024, 1), db0 = make_desc(sbase + 16384, 1024, 256, 3);
#pragma unroll 1
    for (int t = 0;; t++) {
        const int st = t % A1_NST;
        mbar_wait(bars + 8 * st, (t / A1_NST) & 1);
        if (t == A1_SKEW && wg == 0) mbar_wait(bars + 160, 0);
        TSTAMP3(1 + t);
        if (t == 0) CSA(0);
        CSK(6 + t);
        wgmma_fence();
#pragma unroll
        for (int kk = 0; kk < 4; kk++) wgmma_n240<L, 1>(acc, da0 + (uint32_t)(st * (A1_STAGE / 16) + kk * (L ? 128 : 2)), db0 + (uint32_t)(st * (A1_STAGE / 16) + (kk >> 1) * (WQ_STAGE / 32) + (kk & 1) * 32), kk ? 1 : t);
        wgmma_commit();
        if (t == 9) break;
        if (t == A1_SKEW - 1 && wg == 0) wgmma_wait<0>(); else wgmma_wait<1>();
        if (t > 0 && (threadIdx.x & 127) == 0) {
            if (t != A1_SKEW || wg) mbar_arrive(bars + 8 * (A1_NST + (t - 1) % A1_NST));
            if (t == A1_SKEW - 1 && wg == 0) mbar_arrive(bars + 8 * (A1_NST + t % A1_NST));
        }
    }
}

template <bool MAP>
__global__ void __launch_bounds__(A1_THREADS, 1) a1_kernel(const __grid_constant__ Par in, const __grid_constant__ CUtensorMap tmX, const __grid_constant__ CUtensorMap tmR,
                                                           const __grid_constant__ CUtensorMap tmX1, const __grid_constant__ KgMaps tmW, const __grid_constant__ TileTab tab) {
#define layer in.layer
    const unsigned char* const wo = reinterpret_cast<const unsigned char*>(in.wop);
    float2* const rsum = reinterpret_cast<float2*>(in.sum);
    uint4* const of = in.of;
    extern __shared__ __align__(1024) unsigned char stg[];
    const uint32_t sbase = smem_u32(stg);
    const uint32_t bars = sbase + A1_SM_BAR;
    const uint32_t bar_stat = bars + 64, bar_kv = bars + 72, bar_rd = bars + 168;
    const uint32_t bar_wo = bars + 208, bar_done = bars + 216, bar_pv = bars + 224, bar_kvf = bars + 232, bar_f2 = bars + 248, bar_e2 = bars + 384, que = bars + 448;
    const int tid = threadIdx.x;
    CSK(0);
    const int w = __shfl_sync(~0u, tid >> 5, 0), wg = w >> 2;
    uint32_t smid;
    asm volatile("mov.u32 %0, %smid;" : "=r"(smid));
    const uint4 tv = tab.e[(MAP ? smid : blockIdx.x) + (tid & (smid >> 12))];
    const bool one = elect();
    uint32_t tz;
    const unsigned char* wq;
    auto entry = [&] { tz = __shfl_sync(~0u, tv.z, 0); wq = (const unsigned char*)(((uint64_t)__shfl_sync(~0u, tv.y, 0) << 32) | __shfl_sync(~0u, tv.x, 0)); };
    auto issue_w = [&](unsigned it) { bulk_load(sbase + (it % A1_NST) * A1_STAGE + 16384, wq + it * WQ_STAGE, WQ_STAGE, bars + 8 * (it % A1_NST)); };
    auto issue_x = [&](unsigned it, int kb) {
        asm volatile("cp.async.bulk.tensor.5d.shared::cluster.global.mbarrier::complete_tx::bytes [%0], [%1, {%3, %3, %3, %4, %5}], [%2];"
                     ::"r"(sbase + (it % A1_NST) * A1_STAGE), "l"(&tmX), "r"(bars + 8 * (it % A1_NST)), "r"(0), "r"(tz & 15), "r"(kb) : "memory");
    };
    auto first_x = [&] {
        issue_x(0, (tz >> 16) & 7); issue_x(1, ((tz >> 16) & 7) + 1);
    };
    auto expect = [&] {
#pragma unroll
        for (int i = 0; i < A1_NST; i++) mbar_expect_tx(bars + 8 * i, A1_STAGE);
    };
    if (w == 8) {
        if (one) {
            prefetch_tmap(&tmX); prefetch_tmap(&tmW.q);
#pragma unroll
            for (int i = 0; i < A1_NST; i++) mbar_init(bars + 8 * i, 1);
            asm volatile("fence.mbarrier_init.release.cluster;" ::: "memory");
        }
        __syncwarp();
        asm volatile("bar.arrive 0, 384;" ::: "memory");
        if (smid >> 12) __trap();
        entry();
        if ((tz & 0x80000010u) == 16 && one) {
            issue_w(0);
            asm volatile("griddepcontrol.wait;" ::: "memory");
            first_x();
            issue_w(1);
            expect();
            asm volatile("griddepcontrol.launch_dependents;" ::: "memory");
        }
        __syncwarp();
        if (!(tz & 16) && blockIdx.x < 128) kgen_first(in, tmW, sbase + A1_SM_W0, bars - 24, one);
        __syncwarp();
    }
    if (w > 7) CSK(8);
    const bool gen = w != 8 && in.logA && blockIdx.x < 128;
    KgPar kp;
    const int w11 = w < 8 ? 2 * (w & 3) + (w >> 2) : w - 1;
    if (gen) kgen_load(in, w11, kp);
    if (w > 7) CSK(9);
    if (w == 8) {
        const int tile = tz >> 24, mb = tz & 15, hg = (tz >> 8) & 7, kb0 = (tz >> 16) & 7;
        const unsigned l1 = (tz >> 4) & 1;
        if (__builtin_expect(!l1, 0)) {
            CSK(1);
            const uint32_t ep = ld_epoch();
            if (one) kgen_side(in, sbase + A1_SM_W0, bars - 24, [&] { if (tile < 128) { first_x(); issue_x(2, kb0 + 2); expect(); } });
            __syncwarp();
            asm volatile("bar.arrive 10, 96;" ::: "memory");
            CSK(6);
            if (tile < 128) {
                await_all(32, ep * gridDim.x);
                if (one) { issue_w(0); issue_w(1); issue_w(2); }
            }
            CSK(7);
            asm volatile("bar.sync 3, 384;" ::: "memory");
            if (tile < 128 && one) {
                fence_async_smem();
                issue_x(3, kb0 + 3); issue_w(3);
                mbar_expect_tx(bars + 240, 20480);
                bulk_load(sbase + A1_SM_W0, in.x + (size_t)(mb * 128 + hg * 16) * DM, 20480, bars + 240);
            }
            __syncwarp();
            CSK(9);
        } else asm volatile("bar.sync 3, 64;" ::: "memory");
        if (tile < 128 && elect()) {
#pragma unroll 1
            for (unsigned kb = 4 - 2 * l1; kb < 10; kb++) {
                if (kb < A1_NST) mbar_wait(bars + 8 * A1_PW, 0);
                else {
                    mbar_wait(bars + 8 * (A1_NST + kb % A1_NST), ((kb / A1_NST) - 1) & 1);
                    if (l1 && kb < 9) mbar_wait(bar_rd + 8 * (kb - A1_NST), 0);
                    mbar_expect_tx(bars + 8 * (kb % A1_NST), A1_STAGE);
                }
                issue_x(kb, kb < 5 ? kb + kb0 : kb - kb0); issue_w(kb);
                CSK(6 + kb);
                if (kb == (l1 ? A1_WOAT : 9)) {
                    if (!l1) { mbar_wait(bar_stat, 0); asm volatile("fence.proxy.async.global;" ::: "memory"); }
                    mbar_expect_tx(bar_wo, 8 * WOB);
                    bulk_load(sbase + A1_SM_W0, wo + hg * 8 * WOB, 2 * WOB, bar_wo);
                }
            }
            mbar_wait(bars + 8 * (A1_NST + 3), 1);
            bulk_load(sbase + A1_SM_W3, wo + (hg * 8 + 3) * WOB, 3 * WOB, bar_wo);
        }
        CSA(4); CSA_END;
        return;
    }
    {
        if (w < 8 && one) {
#pragma unroll 1
            for (uint32_t c = (w & 4 ? w & 2 ? 0x1111112'01111111ull : 0x1111111'01111184ull : w & 2 ? 0x3122222'01111111ull : 0x1111132'02220000ull) >> (32 * (w & 1)), b = bars + 56 * w; c; c >>= 4, b += 8)
                if (c & 15) mbar_init(b, c & 15);
            asm volatile("fence.mbarrier_init.release.cluster;" ::: "memory");
        }
        __syncwarp();
        asm volatile("bar.sync 0, 384;" ::: "memory");
        if (layer) {
            if (w == 9) asm volatile("bar.arrive 3, 64;" ::: "memory");
        } else {
            if (gen) { SPAN(0, 0); SPAN(0, 1); kgen_tables(in, reinterpret_cast<uint4*>(stg + 3 * A1_STAGE), w11, kp); }
            else if (w != 11 && w11 > 1) asm volatile("bar.arrive 9, 352;" ::: "memory");
            __syncwarp();
            if (w11 < 2) {
                asm volatile("bar.sync 10, 96;" ::: "memory");
                kgen_sums(in, sbase + A1_SM_W0, w11);
                __syncwarp();
                asm volatile("bar.arrive 9, 352;" ::: "memory");
                CSK(1);
            }
            if (w == 9) asm volatile("bar.sync 3, 384;" ::: "memory"); else asm volatile("bar.arrive 3, 384;" ::: "memory");
        }
    }
    tz = __shfl_sync(~0u, tv.z, 0);
    const int tile = tz >> 24, mb = tz & 15, hg = (tz >> 8) & 7;
    float2* rst = reinterpret_cast<float2*>(stg + A1_SM_RS) + 8;
    if (wg == 2) {
        if (w == 11 && layer == 0) {
            asm volatile("bar.sync 9, 352;" ::: "memory");
            CSK(5);
            if (one) publish(64);
            __syncwarp();
            CSK(6);
        }
        if (tile >= 128) { sm_idle(layer); return; }
        if (w == 10) {
            if (one) { prefetch_tmap(&tmR); prefetch_tmap(&tmX1); }
            uint32_t ns;
            asm volatile("mov.u32 %0, %nsmid;" : "=r"(ns));
            if (MAP && ns != 132) __trap();
        }
        __syncwarp();
        if (w == 9) {
            if (layer && one) {
                mbar_expect_tx(bar_stat, 3840);
                bulk_load(sbase + A1_SM_XB, g_xb + tile * 240, 3840, bar_stat);
            }
            __syncwarp();
            uint4* pre = of + (mb * 8 + hg) * 1280 + (tid - 288);
#pragma unroll 1
            for (int k = 0; k < 5 + 5 * layer; k++) {
#pragma unroll
                for (int i = 0; i < 8; i++) asm volatile("st.global.v4.u32 [%0], {%1,%1,%1,%1};" ::"l"(pre + 32 * i), "r"(~0u) : "memory");
                pre += k < 5 ? 256 : XCP / 8;
                if (k == 4) {
                    CSA(2);
                    asm volatile("fence.acq_rel.gpu;" ::: "memory");
                    asm volatile("fence.proxy.async.global;" ::: "memory");
                    __syncwarp();
                    if (tid == 288) mbar_arrive(bar_done);
                    CSA(3);
                    pre = reinterpret_cast<uint4*>(g_yT) + tile * (5 * XCP / 8) + (tid - 288);
                }
            }
            if (layer == 0) {
                asm volatile("griddepcontrol.launch_dependents;" ::: "memory");
                await_all(64, ld_epoch() * gridDim.x);
                CSA(5);
                float4 a[2] = {};
#pragma unroll
                for (int k = 0; k < 10; k++)
#pragma unroll
                    for (int h = 0; h < 2; h++) {
                        const int c4 = min(tid - 288 + 32 * h, 59);
                        const float4 v = __ldcg(reinterpret_cast<const float4*>(g_csp + (k / 5) * 9600 + (k % 5) * 640 + hg * 80) + c4 + (c4 / 20) * 780);
                        a[h].x += v.x; a[h].y += v.y; a[h].z += v.z; a[h].w += v.w;
                    }
#pragma unroll
                for (int h = 0; h < 2; h++)
#pragma unroll
                    for (int k = 0; k < 4; k++) {
                        const float c = 0.5f * (k == 0 ? a[h].x : k == 1 ? a[h].y : k == 2 ? a[h].z : a[h].w), c1 = c - rbf(c), c2 = c1 - rbf(c1);
                        *reinterpret_cast<uint4*>(stg + A1_SM_XB + (4 * min(tid - 288 + 32 * h, 59) + k) * 16) = make_uint4(pack2(c, c1), pack2(c2, 0.f), 0u, 0u);
                    }
                fence_async_smem();
                __syncwarp();
                if (one) {
                    bulk_store(g_xb + tile * 240, sbase + A1_SM_XB, 3840);
                    asm volatile("cp.async.bulk.commit_group;" ::: "memory");
                    asm volatile("cp.async.bulk.wait_group.read 0;" ::: "memory");
                    mbar_arrive(bar_stat);
                }
                __syncwarp();
                CSA(1);
            }
            TSTAMP1T(9, 288);
        } else {
            const int j = tid - 320;
            const uint32_t tag = ld_epoch();
            if (tid == 352) sm_started(layer);
            const int ch = j & 7, kg = (j >> 3) & 3;
            const unsigned char* src = stg + (layer ? (j >> 5) * 8192 + (hg & 3) * 2048 : A1_SM_W0 + (j >> 2) * 1280);
            const int of0 = layer ? kg * 128 + ((ch ^ kg) << 4) : (j & 7) << 4, ofx = layer ? 576 : 64, ofy = layer ? 1024 : 128;
            float s[8], q[8], p0[8];
#pragma unroll
            for (int i = 0; i < 8; i++) { s[i] = 0.f; q[i] = 0.f; }
#pragma unroll 1
            for (int it = 0; it < 5; it++) {
                uint4 v[4];
                mbar_wait(layer ? bars + 8 * (it % A1_NST) : bars + 240, layer * it / A1_NST);
#pragma unroll
                for (int k = 0; k < 4; k++) v[k] = *reinterpret_cast<const uint4*>(src + (layer ? (it % A1_NST) * A1_STAGE : it * 256) + (k & 1 ? of0 ^ ofx : of0) + (k >> 1) * ofy);
                if (it == 0) {
                    const uint4 pv = *reinterpret_cast<const uint4*>(src + (layer ? ch << 4 : 0));
                    const uint32_t w[4] = {pv.x, pv.y, pv.z, pv.w};
#pragma unroll
                    for (int i = 0; i < 4; i++) { p0[2 * i] = __uint_as_float((layer ? w[i] : w[0]) << 16); p0[2 * i + 1] = __uint_as_float(layer ? w[i] & 0xffff0000u : w[0] << 16); }
                }
                asm volatile("" :: "r"(v[0].x), "r"(v[1].x), "r"(v[2].x), "r"(v[3].x), "f"(p0[0]) : "memory");
                __syncwarp();
                if ((tid & 31) == 0) mbar_arrive(bar_rd + 8 * it);
#pragma unroll
                for (int k = 0; k < 4; k++) {
                    const uint32_t w[4] = {v[k].x, v[k].y, v[k].z, v[k].w};
#pragma unroll
                    for (int i = 0; i < 4; i++) {
                        const float a = __uint_as_float(w[i] << 16) - p0[2 * i], b = __uint_as_float(w[i] & 0xffff0000u) - p0[2 * i + 1];
                        s[2 * i] += a; s[2 * i + 1] += b; q[2 * i] = fmaf(a, a, q[2 * i]); q[2 * i + 1] = fmaf(b, b, q[2 * i + 1]);
                    }
                }
            }
            float o[4];
            int row;
            if (layer == 0) {
                float s0 = ((s[0] + s[1]) + (s[2] + s[3])) + ((s[4] + s[5]) + (s[6] + s[7])), q0 = ((q[0] + q[1]) + (q[2] + q[3])) + ((q[4] + q[5]) + (q[6] + q[7]));
#pragma unroll
                for (int o = 1; o <= 2; o <<= 1) { s0 += __shfl_xor_sync(~0u, s0, o); q0 += __shfl_xor_sync(~0u, q0, o); }
                if ((j & 3) == 0) {
                    const float d = s0 * (1.0f / DM);
                    const uint32_t ms = pack2(p0[0] + d, sqrt_apx(rbf(rbf(fmaxf(fmaf(-d, d, q0 * (1.0f / DM)), 0.f)) + 1e-5f)));
                    asm volatile("st.global.cg.u64 [%0], %1;" ::"l"(g_rstat + mb * 128 + (j & 4) * 16 + hg * 8 + (j >> 3)), "l"(tagw(ms, tag)) : "memory");
                    g_piv[mb * 128 + hg * 16 + ((j >> 2) & 8) + (j & 4) + ((j >> 3) & 3)] = __ushort_as_bfloat16((unsigned short)ms);
                }
                ulonglong2 v;
#pragma unroll 1
                for (int it = 0; it < SPIN_MAX; it++) {
                    v = ld_tag2(reinterpret_cast<const ulonglong2*>(g_rstat + mb * 128) + j);
                    if (tag_ok(v, tag)) break;
                    __nanosleep(100);
                }
                o[0] = __uint_as_float((uint32_t)v.x << 16); o[1] = rcp_apx(__uint_as_float((uint32_t)v.x & 0xffff0000u));
                o[2] = __uint_as_float((uint32_t)v.y << 16); o[3] = rcp_apx(__uint_as_float((uint32_t)v.y & 0xffff0000u));
                row = 2 * j;
            } else {
#pragma unroll
                for (int i = 0; i < 4; i++) {
                    const bool up = kg & 2;
                    const float ss = __shfl_xor_sync(~0u, up ? s[i] : s[i + 4], 16), qq = __shfl_xor_sync(~0u, up ? q[i] : q[i + 4], 16);
                    s[i] = (up ? s[i + 4] : s[i]) + ss; q[i] = (up ? q[i + 4] : q[i]) + qq; p0[i] = up ? p0[i + 4] : p0[i];
                }
#pragma unroll
                for (int i = 0; i < 2; i++) {
                    const bool up = kg & 1;
                    const float ss = __shfl_xor_sync(~0u, up ? s[i] : s[i + 2], 8), qq = __shfl_xor_sync(~0u, up ? q[i] : q[i + 2], 8);
                    s[i] = (up ? s[i + 2] : s[i]) + ss; q[i] = (up ? q[i + 2] : q[i]) + qq; p0[i] = up ? p0[i + 2] : p0[i];
                }
                uint4* gp = g_halo + 86016 + mb * 512 + j;
                const float d0 = s[0] * (1.0f / 80.0f), d1 = s[1] * (1.0f / 80.0f);
                asm volatile("st.relaxed.gpu.global.v4.f32 [%0], {%1,%2,%3,%4};" ::"l"(gp + hg * 64), "f"(p0[0] + d0), "f"(fmaxf(fmaf(-d0, s[0], q[0]), 0.f)), "f"(p0[1] + d1), "f"(fmaxf(fmaf(-d1, s[1], q[1]), 0.f)) : "memory");
                __nanosleep(ST_SLEEP0);
                uint32_t pw[8][4], todo = 0xff;
#pragma unroll 1
                for (int it = 0; it < SPIN_MAX; it++) {
#pragma unroll
                    for (int k = 0; k < 8; k++)
                        if (todo >> k & 1) asm volatile("ld.relaxed.gpu.global.v4.u32 {%0,%1,%2,%3}, [%4];" : "=r"(pw[k][0]), "=r"(pw[k][1]), "=r"(pw[k][2]), "=r"(pw[k][3]) : "l"(gp + k * 64) : "memory");
#pragma unroll
                    for (int k = 0; k < 8; k++)
                        if (__all_sync(~0u, pw[k][0] != ~0u && pw[k][1] != ~0u && pw[k][2] != ~0u && pw[k][3] != ~0u)) todo &= ~(1u << k);
                    if (!todo) break;
                    __nanosleep(ST_SLEEP);
                }
#pragma unroll
                for (int r = 0; r < 2; r++) {
                    float mean = 0.f, m2 = 0.f;
#pragma unroll
                    for (int k = 0; k < 8; k++) mean += __uint_as_float(pw[k][2 * r]);
                    mean *= 0.125f;
#pragma unroll
                    for (int k = 0; k < 8; k++) {
                        const float dm = __uint_as_float(pw[k][2 * r]) - mean;
                        m2 += fmaf(80.0f * dm, dm, __uint_as_float(pw[k][2 * r + 1]));
                    }
                    o[2 * r] = rbf(mean);
                    o[2 * r + 1] = rcp_apx(rbf(sqrt_apx(rbf(rbf(m2 * (1.0f / DM)) + 1e-5f))));
                }
                row = (j >> 5) * 64 + (j & 7) * 8 + ((j >> 3) & 3) * 2;
                if (hg == 0) *reinterpret_cast<uint32_t*>(g_piv + SEQ + mb * 128 + 2 * (row & 60) + 4 * (row >> 6) + (row & 3)) = __byte_perm(__float_as_uint(o[0]), __float_as_uint(o[2]), 0x7632);
            }
#pragma unroll
            for (int r = 0; r < 2; r++)
                *reinterpret_cast<uint4*>(stg + A1_SM_XA + (row + r) * 16) = make_uint4(__byte_perm(__float_as_uint(-o[2 * r]), 0, 0x3232), __float_as_uint(-o[2 * r]) >> 16, 0u, 0u);
            *reinterpret_cast<float4*>(rst + row + (row >> 6) * 8) = make_float4(o[0], o[1], o[2], o[3]);
            fence_async_smem();
            TSTAMP1T(7, 320); CSA(1);
            if (tid == 320) DBGC(44);
            __syncwarp();
            if ((tid & 31) == 0) mbar_arrive(bar_stat);
        }
        CSA(4); CSA_END;
        if (tid == 320) DBGCAL(0);
        if (tid == WOT) {
            mbar_wait(WO_LATE, 0);
            mbar_wait(bar_done, 0);
            bulk_load(sbase, wo + (hg * 8 + 6) * WOB, 2 * WOB, bar_wo);
            bulk_load(sbase + A1_SM_W0 + 2 * WOB, wo + (hg * 8 + 2) * WOB, WOB, bar_wo);
        }
        __syncwarp();
#define FWA 11
#define FWB 10
        if (w == FWA || w == FWB) {
            const int cw = w == FWB;
            const uint32_t* fl = reinterpret_cast<const uint32_t*>(rsum + 2 * SEQ) + (((layer * 16 + mb) * 2 + cw) * 8 + (tid & 7)) * FSTR;
            const unsigned char* src = reinterpret_cast<const unsigned char*>(of) + mb * 163840 + cw * 10240 + (tid & 7) * 20480;
            const uint32_t sl = sbase + (cw ? A1_SM_A1 : A1_SM_A0);
            mbar_wait(cw ? bar_done : bar_kvf, 0);
            if ((tid & 31) == 0) {
                mbar_expect_tx(bar_f2 + 64 * cw + 64, 10240);
                tma_load_3d(sl + 51200, &tmR, layer ? 0 : hg * 80, layer ? hg * 80 : mb * 64, layer ? mb * 2 + cw : cw, bar_f2 + 64 * cw + 64);
            }
            __syncwarp();
            uint32_t pend = 0xffu & ~(1u << hg), v = 0;
            const uint32_t bo = wo_off((tid & 7) + ((tid & 7) < hg)) >> 4, lt = (1u << (tid & 31)) - 1;
#pragma unroll 1
            for (int it = 0; pend && it < 2 * SPIN_MAX; it++) {
                if (v != 4 && (pend >> (tid & 31) & 1)) asm volatile(A1_FLD " %0, [%1];" : "=r"(v) : "l"(fl) : "memory");
                uint32_t fr;
                asm volatile("{\n.reg .pred p;\nmbarrier.test_wait.parity.shared::cta.b64 p, [%1], 0;\nselp.b32 %0, 1, 0, p;\n}" : "=r"(fr) : "r"(bar_e2 + 16 * cw + (tid & 1) * 8) : "memory");
                fr = __ballot_sync(~0u, fr);
                uint32_t m = __ballot_sync(~0u, v == 4 || it >= A1_FSPIN) & pend;
                const int q = 8 - __popc(pend) + __popc(m & lt);
                m &= __ballot_sync(~0u, q < ((fr & 2) ? 8 : (fr & 1) ? 7 : 5));
                pend ^= m;
                if (m >> (tid & 31) & 1) DBGC(12 + cw * 8 + (tid & 7));
                if (!m) __nanosleep(A1_FSLEEP);
                else asm volatile("fence.proxy.async.global;" ::: "memory");
                if (m >> (tid & 31) & 1) {
                    bulk_load(q == 7 && !cw ? sbase + A1_SM_W0 : sl + (q < 6 ? q : q - 6) * 10240, src, 10240, bar_f2 + 64 * cw + 8 * q);
                    asm volatile("st.shared.u32 [%0], %1;" ::"r"(que + 32 * cw + 4 * q), "r"(bo) : "memory");
                    mbar_expect_tx(bar_f2 + 64 * cw + 8 * q, 10240);
                    DBGC(44 + cw * 8 + q);
                }
                __syncwarp();
            }
        }
    } else if (tile < 128) {
        SPAN(1 + 4 * layer, 0);
        constexpr int on = 1;
        float acc[120];
        const int lane = tid & 31, warp = w & 7, g = lane >> 2, t = lane & 3;
        if (on) {
            SPAN(1 + 4 * layer, 1);
            TSTAMP1(0);
            if (threadIdx.x == 0) { GSTAMP(g_tim1, 15); }
            TSTAMP3(0);
            if (tid == 0) TSTAMP2(0);
            TSTAMP4(0);
            if (tid == 0) DBGC(60);
            if (layer == 0) a1_mainloop<0>(acc, sbase, bars, wg, tile); else a1_mainloop<1>(acc, sbase, bars, wg, tile);
            uint32_t ok;
            asm volatile("{\n.reg .pred p;\nmbarrier.test_wait.parity.shared::cta.b64 p, [%1], 0;\nselp.b32 %0, 1, 0, p;\n}" : "=r"(ok) : "r"(bar_stat) : "memory");
            if (tid == 128 && !ok) mbar_arrive(bars + 160);
            __syncwarp();
            mbar_wait(bar_stat, 0);
            wgmma_fence();
            wgmma_n240<0, 0>(acc, make_desc(sbase + A1_SM_XA + wg * 1024, 0, 128, 0), make_desc(sbase + A1_SM_XB, 0, 128, 0), 1);
            wgmma_commit();
            if (tid == 128 && ok) mbar_arrive(bars + 160);
            mbar_wait(bars + 8 * (A1_NST + 3), 1);
        }
        const float2* rw = rst + 16 * warp + 8 * wg;
        const float rb0 = rw[g + 8].y, ra = rw[g].y * 0.22360679774997896f, rb = rb0 * 0.22360679774997896f;
        wgmma_wait<0>();
        if ((tid & 127) == 0) mbar_arrive(bar_done);
        TSTAMP1(2); CSA(1);
        TSTAMP1T(13, 224);
        if ((tid & 127) == 0) DBGC(62 - wg);
        uint32_t f[2][30];
#pragma unroll
        for (int j = 10; j < 30; j++) f[1][j] = pack2(acc[4 * j + 2], acc[4 * j + 3]);
        if ((warp & 3) == 3) {
            uint4* hout = g_halo + (((layer * 16 + mb) * 8 + hg) * 2 + wg) * 168;
#pragma unroll
            for (int j = 0; j < 20; j += 4)
                asm volatile("st.relaxed.gpu.global.v4.u32 [%0], {%1,%2,%3,%4};" ::"l"(hout + 8 * j + lane), "r"(f[1][10 + j]), "r"(f[1][11 + j]), "r"(f[1][12 + j]), "r"(f[1][13 + j]) : "memory");
            if (t == 0) asm volatile("st.relaxed.gpu.global.f32 [%0], %1;" ::"l"(reinterpret_cast<float*>(hout + 160) + g), "f"(rb0) : "memory");
        }
        TSTAMP1T(12, 224);
        const uint32_t kvw = sbase + A1_SM_KV + (16 * warp + 8 * wg) * A1_KVP;
        const uint32_t mrow = kvw + (lane & 7) * A1_KVP + (lane >> 3) * 16;
#pragma unroll
        for (int j = 0; j < 20; j += 4) stsm_x4(mrow + 16 * A1_KVP + 16 * j, f[1][10 + j], f[1][11 + j], f[1][12 + j], f[1][13 + j]);
        __syncwarp();
        if (lane == 0 && (warp & 3) != 3) mbar_arrive(bar_kv + 8 * (warp + 1));
#pragma unroll
        for (int j = 0; j < 30; j++) f[0][j] = pack2(acc[4 * j], acc[4 * j + 1]);
        stsm_x4(mrow + 8 * A1_KVP + 160, f[0][20], f[0][21], f[0][22], f[0][23]);
        stsm_x4(mrow + 8 * A1_KVP + 224, f[0][24], f[0][25], f[0][26], f[0][27]);
        asm volatile("stmatrix.sync.aligned.m8n8.x2.shared.b16 [%0], {%1,%2};" ::"r"(mrow + 8 * A1_KVP + 288), "r"(f[0][28]), "r"(f[0][29]) : "memory");
#pragma unroll
        for (int j = 0; j < 10; j++) f[1][j] = pack2(acc[4 * j + 2], acc[4 * j + 3]);
        __syncwarp();
        uint32_t vb[10][2], vp[12], kp[12];
#pragma unroll
        for (int j = 0; j < 10; j += 2) ldsm_x4_t(&vb[j][0], kvw + (8 + (lane & 15)) * A1_KVP + 160 + (lane >> 4) * 16 + 16 * j);
        const bool up0 = 2 * t > g, up1 = 2 * t + 1 > g, edge = (mb | (warp & 3)) == 0;
        float rk[4];
        auto above = [&]() {
            mbar_wait(bar_kv + 8 * warp, 0);
#pragma unroll
            for (int j = 0; j < 12; j += 4) ldsm_x4(&kp[j], mrow + 16 * j);
            rk[0] = rw[2 * t - (up0 ? 8 : 0)].y; rk[1] = rw[2 * t + 1 - (up1 ? 8 : 0)].y;
#pragma unroll
            for (int j = 0; j < 12; j += 4) ldsm_x4_t(&vp[j], mrow + 160 + 16 * j - (j == 8 ? (lane & 16) * 2 : 0));
            __syncwarp();
            if (lane == 0) mbar_arrive(bar_kvf);
        };
        auto halo = [&]() {
            if (lane == 0) mbar_arrive(bar_kvf);
            const uint4* hin = g_halo + (((layer * 16 + mb - 1) * 8 + hg) * 2 + wg) * 168;
            uint32_t hv[22] = {};
            rk[0] = rw[2 * t].y; rk[1] = rw[2 * t + 1].y;
            if (mb > 0) {
#pragma unroll 1
                for (int it = 0; it < SPIN_MAX; it++) {
#pragma unroll
                    for (int k = 0; k < 20; k += 4)
                        asm volatile("ld.relaxed.gpu.global.v4.u32 {%0,%1,%2,%3}, [%4];" : "=r"(hv[k]), "=r"(hv[k + 1]), "=r"(hv[k + 2]), "=r"(hv[k + 3]) : "l"(hin + 8 * k + lane) : "memory");
                    asm volatile("ld.relaxed.gpu.global.v2.u32 {%0,%1}, [%2];" : "=r"(hv[20]), "=r"(hv[21]) : "l"(reinterpret_cast<const uint2*>(hin + 160) + t) : "memory");
                    uint32_t m = max(hv[20], hv[21]);
#pragma unroll
                    for (int k = 0; k < 20; k += 2) m = __vimax3_u32(m, hv[k], hv[k + 1]);
                    if (!__any_sync(~0u, m == ~0u)) break;
                }
            }
            if (lane == 0) DBGC(52 - 16 * wg);
#pragma unroll
            for (int j = 0; j < 10; j++) {
                kp[j] = hv[j];
                asm volatile("movmatrix.sync.aligned.m8n8.trans.b16 %0, %1;" : "=r"(vp[j]) : "r"(hv[10 + j]));
            }
            if (up0) rk[0] = __uint_as_float(hv[20]);
            if (up1) rk[1] = __uint_as_float(hv[21]);
        };
        rk[2] = rw[2 * t + (up0 ? 0 : 8)].y; rk[3] = rw[2 * t + 1 + (up1 ? 0 : 8)].y;
        uint32_t qs[4][2];
#pragma unroll
        for (int h = 0; h < 4; h++) {
            qs[h][0] = (t >> 1) == (h & 1) ? f[0][5 * (h >> 1) + 2] : 0u; qs[h][1] = (t >> 1) == (h & 1) ? f[1][5 * (h >> 1) + 2] : 0u;
            asm volatile("" : "+r"(qs[h][0]), "+r"(qs[h][1]));
        }
#pragma unroll
        for (int j = 0; j < 10; j++) asm volatile("" : "+r"(f[0][j]), "+r"(f[1][j]), "+r"(f[0][10 + j]));
        if (warp & 3) above(); else if (wg) halo();
        TSTAMP1T(10, 64); CSA(2);
        if (warp && !wg) mbar_wait(bars + 416 + 8 * warp, 0);
        CSA(3);
        float sc[4][3][4];
#pragma unroll
        for (int h = 0; h < 4; h++) {
            const int jb = 5 * (h >> 1) + 3 * (h & 1), js = 5 * (h >> 1) + 2;
#pragma unroll
            for (int nt = 1; nt < 3; nt++) {
#pragma unroll
                for (int e = 0; e < 4; e++) sc[h][nt][e] = 0.f;
                mma_bf16(sc[h][nt], f[0][jb], f[1][jb], f[0][jb + 1], f[1][jb + 1], f[nt - 1][10 + jb], f[nt - 1][11 + jb]);
                mma_bf16_k8(sc[h][nt], qs[h][0], qs[h][1], f[nt - 1][10 + js]);
            }
        }
        if (warp == 0) halo();
        TSTAMP1(8); CSA(4);
#pragma unroll
        for (int h = 0; h < 4; h++) {
            const int jb = 5 * (h >> 1) + 3 * (h & 1), js = 5 * (h >> 1) + 2;
#pragma unroll
            for (int e = 0; e < 4; e++) sc[h][0][e] = 0.f;
            mma_bf16(sc[h][0], f[0][jb], f[1][jb], f[0][jb + 1], f[1][jb + 1], kp[jb], kp[jb + 1]);
            mma_bf16_k8(sc[h][0], qs[h][0], qs[h][1], kp[js]);
        }
        TSTAMP1T(3, 64);
        float p[4][4], sum[4][2];
        uint32_t lg[4][2], mx[4];
        const float rl[4] = {rk[0] * ra, rk[1] * ra, rk[2] * rb, rk[3] * rb};
        auto max2 = [](uint32_t a, uint32_t b) { uint32_t r; asm("max.bf16x2 %0, %1, %2;" : "=r"(r) : "r"(a), "r"(b)); return r; };
#pragma unroll
        for (int h = 0; h < 4; h++) {
            lg[h][0] = pack2((up0 ? sc[h][0][0] : sc[h][1][0]) * rl[0], (up0 ? sc[h][1][2] : sc[h][2][2]) * rl[2]);
            lg[h][1] = pack2((up1 ? sc[h][0][1] : sc[h][1][1]) * rl[1], (up1 ? sc[h][1][3] : sc[h][2][3]) * rl[3]);
            if (edge) {
                if (up0) lg[h][0] = __byte_perm(lg[h][0], 0xce6eu, 0x3254);
                if (up1) lg[h][1] = __byte_perm(lg[h][1], 0xce6eu, 0x3254);
            }
            mx[h] = max2(lg[h][0], lg[h][1]);
        }
#pragma unroll
        for (int o = 1; o <= 2; o <<= 1)
#pragma unroll
            for (int h = 0; h < 4; h++) mx[h] = max2(mx[h], __shfl_xor_sync(~0u, mx[h], o));
#pragma unroll
        for (int h = 0; h < 4; h++)
#pragma unroll
            for (int r = 0; r < 2; r++) {
                const float m = __uint_as_float(r ? mx[h] & 0xffff0000u : mx[h] << 16);
#pragma unroll
                for (int e = 0; e < 2; e++)
                    asm("ex2.approx.ftz.f32 %0, %1;" : "=f"(p[h][2 * r + e]) : "f"((__uint_as_float(r ? lg[h][e] & 0xffff0000u : lg[h][e] << 16) - m) * 1.4426950408889634f));
                sum[h][r] = p[h][2 * r] + p[h][2 * r + 1];
            }
#pragma unroll
        for (int o = 1; o <= 2; o <<= 1)
#pragma unroll
            for (int h = 0; h < 4; h++)
#pragma unroll
                for (int r = 0; r < 2; r++) sum[h][r] += __shfl_xor_sync(~0u, sum[h][r], o);
        TSTAMP1T(5, 64); CSA(5);
        const uint32_t mu = (up0 ? 0xffffu : 0u) | (up1 ? 0xffff0000u : 0u);
        uint32_t ob[10][2];
#pragma unroll
        for (int P = 0; P < 2; P++) {
            float os[2][4];
#pragma unroll
            for (int e = 0; e < 2; e++) {
                const int h = 2 * P + e;
                const float i0 = rcp_apx(sum[h][0]), i1 = rcp_apx(sum[h][1]);
                const uint32_t w0 = pack2(p[h][0] * rk[0] * i0, p[h][1] * rk[1] * i0), w1 = pack2(p[h][2] * rk[2] * i1, p[h][3] * rk[3] * i1);
#pragma unroll
                for (int dt = 0; dt < 3; dt++) {
                    const int j = 5 * P + (dt < 2 ? 3 * e + dt : 2);
                    float o[4] = {0.f, 0.f, 0.f, 0.f};
                    mma_bf16(o, w0 & ~mu, w1 & mu, 0u, w1 & ~mu, vb[j][0], vb[j][1]);
                    mma_bf16_k8(o, w0 & mu, 0u, vp[j]);
                    if (dt < 2) { ob[j][0] = pack2(o[0], o[1]); ob[j][1] = pack2(o[2], o[3]); }
                    else { os[e][0] = o[0]; os[e][1] = o[1]; os[e][2] = o[2]; os[e][3] = o[3]; }
                }
            }
#pragma unroll
            for (int k = 0; k < 4; k++) os[0][k] = t < 2 ? os[0][k] : os[1][k];
            ob[5 * P + 2][0] = pack2(os[0][0], os[0][1]); ob[5 * P + 2][1] = pack2(os[0][2], os[0][3]);
        }
        const uint32_t sl = sbase + (wg ? A1_SM_A1 : A1_SM_A0);
        const uint32_t o0 = (warp & 3) * 2048 + g * 64 + ((t ^ (g >> 1)) << 4), o1 = 8192 + (warp & 3) * 512 + g * 32 + ((t ^ ((g >> 2) << 1)) << 3);
        CSA(15);
        mbar_wait(bar_done, 0);
        if (wg == 0) mbar_wait(bar_kvf, 0);
#pragma unroll
        for (int h = 0; h < 2; h++) {
            asm volatile("st.shared.v4.u32 [%0], {%1,%2,%3,%4};" ::"r"(sl + o0 + h * 1024), "r"(ob[0][h]), "r"(ob[1][h]), "r"(ob[2][h]), "r"(ob[3][h]) : "memory");
            asm volatile("st.shared.v4.u32 [%0], {%1,%2,%3,%4};" ::"r"(sl + o0 + h * 1024 + 512), "r"(ob[4][h]), "r"(ob[5][h]), "r"(ob[6][h]), "r"(ob[7][h]) : "memory");
            asm volatile("st.shared.v2.u32 [%0], {%1,%2};" ::"r"(sl + o1 + h * 256), "r"(ob[8][h]), "r"(ob[9][h]) : "memory");
        }
        if (wg && lane == 0) mbar_arrive(bars + 384 + 8 * warp);
        fence_async_smem();
        __syncwarp();
        TSTAMP1T(4, 64); CSA(6);
        TSTAMP1(1);
        TSTAMP2(1);
        const unsigned char* ot = reinterpret_cast<const unsigned char*>(of) + mb * 163840 + wg * 10240;
        if (lane == 0) {
            asm volatile("cp.async.bulk.global.shared::cta.bulk_group [%0], [%1], 2048;" ::"l"(ot + hg * 20480 + (warp & 3) * 2048), "r"(sl + (warp & 3) * 2048) : "memory");
            asm volatile("cp.async.bulk.global.shared::cta.bulk_group [%0], [%1], 512;" ::"l"(ot + hg * 20480 + 8192 + (warp & 3) * 512), "r"(sl + 8192 + (warp & 3) * 512) : "memory");
            asm volatile("cp.async.bulk.commit_group;" ::: "memory");
            if (wg == 0) mbar_arrive(bar_pv);
            asm volatile("cp.async.bulk.wait_group 0;" ::: "memory");
            asm volatile(A1_FRED " [%0], 1;" ::"l"(reinterpret_cast<uint32_t*>(rsum + 2 * SEQ) + (((layer * 16 + mb) * 2 + wg) * 8 + hg) * FSTR) : "memory");
            DBGC(4 + warp);
        }
        TSTAMP4(11); CSA(7);
        float ac2[40];
        const uint64_t db0 = make_desc(sbase, 1024, 256, 3), db1 = make_desc(sbase + 10240, 512, 256, 3), da0 = make_desc(sl, 16, 1024, 2), da1 = make_desc(sl + 8192, 16, 256, 3);
        const uint32_t o7 = wg ? 640 : (A1_SM_W0 - A1_SM_A0) >> 4;
        const uint32_t trow = ((lane & 7) + 8 * (lane >> 4)) * 128 + (((2 * (warp & 3) + ((lane >> 3) & 1)) ^ (lane & 7)) << 4);
        uint32_t xr[10][2];
        mbar_wait(bar_f2 + 64 * wg + 64, 0);
        if (layer == 0) {
#pragma unroll
            for (int j = 0; j < 10; j += 2) ldsm_x4(&xr[j][0], sl + 51200 + (16 * (warp & 3) + (lane & 15)) * 160 + (lane >> 4) * 16 + 16 * j);
        } else {
#pragma unroll
            for (int j = 0; j < 10; j += 2) ldsm_x4_t(&xr[j][0], sl + 51200 + trow + 1024 * j);
        }
        const uint32_t ri = __shfl_sync(~0u, layer * SEQ + (wg * 2 + ((g >> 1) & 1)) * 512 + (mb * 16 + 4 * (warp & 3) + (g >> 2)) * 2 + (g & 1), lane);
        mbar_wait(bar_wo, 0);
        if (wg) mbar_wait(bar_pv, 0);
        if (wg) asm volatile("bar.sync 2, 128;" ::: "memory"); else asm volatile("bar.sync 1, 128;" ::: "memory");
        TSTAMP2(2); CSA(8);
#pragma unroll
        for (int q = 0; q < 8; q++) {
            uint32_t bo = wo_off(0) >> 4;
            if (q) {
                mbar_wait(bar_f2 + 64 * wg + 8 * q, 0);
                asm volatile("ld.shared.u32 %0, [%1];" : "=r"(bo) : "r"(que + 32 * wg + 4 * q) : "memory");
                bo = __shfl_sync(~0u, bo, 0);
                TSTAMP4(q);
                if (q % 3 == 1) CSA(9 + q / 3);
                if (q == 1 && (tid & 127) == 0) DBGC(29 + 8 * wg);
            }
            wgmma_fence();
#pragma unroll
            for (int j = 0; j < 5; j++) wgmma_n80(ac2, (j < 4 ? da0 : da1) + (q == 7 ? o7 : 0u) + (uint64_t)((q < 6 ? q * 640 : 0) + (j & 2) * 16 + (j & 1) * 2), (j < 4 ? db0 : db1) + bo + (uint64_t)((j & 2) * 160 + (j & 1) * 32), j || q);
            wgmma_commit();
            if (q == 0) {
                wgmma_wait<0>();
                if ((tid & 127) == 0) { mbar_arrive(bar_e2 + 16 * wg); mbar_arrive(bar_e2 + 8); }
            }
            if (q == 2 && wg) {
                wgmma_wait<1>();
                if (tid == 128) mbar_arrive(bar_e2 + 24);
            }
        }
        if ((tid & 127) == 0) DBGC(28 + wg * 8 + 7);
        TSTAMP2(3);
        wgmma_wait<0>();
        TSTAMP2(4); CSA(12);
        if (__any_sync(~0u, ac2[0] != ac2[0] || ac2[2] != ac2[2])) {
#pragma unroll
            for (int i = 0; i < 40; i++) ac2[i] = 0.f;
            uint32_t a[20], an[20];
            auto lda = [&](uint32_t (&r)[20], int h) {
#pragma unroll
                for (int u = 0; u < 4; u++)
                    asm volatile("ld.relaxed.gpu.global.v4.u32 {%0,%1,%2,%3}, [%4];" : "=r"(r[4 * u]), "=r"(r[4 * u + 1]), "=r"(r[4 * u + 2]), "=r"(r[4 * u + 3]) : "l"(ot + h * 20480 + o0 + u * 512) : "memory");
#pragma unroll
                for (int u = 0; u < 2; u++)
                    asm volatile("ld.relaxed.gpu.global.v2.u32 {%0,%1}, [%2];" : "=r"(r[16 + 2 * u]), "=r"(r[17 + 2 * u]) : "l"(ot + h * 20480 + o1 + u * 256) : "memory");
            };
            lda(an, 0);
#pragma unroll 5
            for (int k = lane; k < WOB / 16; k += 32)
                reinterpret_cast<uint4*>(stg + (sl - sbase))[k] = __ldcg(reinterpret_cast<const uint4*>(wo + hg * 8 * WOB) + k);
            __syncwarp();
#pragma unroll 1
            for (int h = 0; h < 8; h++) {
#pragma unroll 1
                for (int it = 0; it < SPIN_MAX; it++) {
                    uint32_t m = 0;
#pragma unroll
                    for (int k = 0; k < 20; k += 2) m = __vimax3_u32(m, an[k], an[k + 1]);
                    if (!__any_sync(~0u, m == ~0u)) break;
                    lda(an, h);
                }
#pragma unroll
                for (int k = 0; k < 20; k++) a[k] = an[k];
                lda(an, min(h + 1, 7));
                const uint32_t bp = h == hg ? sl : sbase + wo_off(h + (h < hg));
                const int r0 = 8 * ((lane & 7) >> 1) + 2 * (lane >> 3) + (lane & 1), r2 = 4 * ((lane & 7) >> 1) + 2 * ((lane >> 3) & 1) + (lane & 1);
#pragma unroll
                for (int n = 0; n < 10; n++) {
                    uint32_t b[12];
                    ldsm_x4_t(b, bp + (n >> 1) * 1024 + r0 * 32 + (((n ^ (r0 >> 2)) & 1) << 4));
                    ldsm_x4_t(b + 4, bp + 5120 + (n >> 1) * 1024 + r0 * 32 + (((n ^ (r0 >> 2)) & 1) << 4));
                    ldsm_x4_t(b + 8, bp + 10240 + (n >> 1) * 512 + r2 * 32 + (((n ^ (r2 >> 2)) & 1) << 4));
                    mma_bf16(ac2 + 4 * n, a[0], a[8], a[1], a[9], b[0], b[1]); mma_bf16(ac2 + 4 * n, a[2], a[10], a[3], a[11], b[2], b[3]);
                    mma_bf16(ac2 + 4 * n, a[4], a[12], a[5], a[13], b[4], b[5]); mma_bf16(ac2 + 4 * n, a[6], a[14], a[7], a[15], b[6], b[7]);
                    mma_bf16(ac2 + 4 * n, a[16], a[18], a[17], a[19], b[8], b[9]);
                }
            }
        }
#pragma unroll
        for (int j = 0; j < 10; j++)
#pragma unroll
            for (int hh = 0; hh < 2; hh++) {
                const uint32_t a = pack2(ac2[4 * j + 2 * hh], ac2[4 * j + 2 * hh + 1]);
                const __nv_bfloat162 r = __hadd2_rn(*reinterpret_cast<const __nv_bfloat162*>(&xr[j][hh]), *reinterpret_cast<const __nv_bfloat162*>(&a));
                xr[j][hh] = *reinterpret_cast<const uint32_t*>(&r);
            }
        const uint32_t so = sl + 30720;
#pragma unroll
        for (int j = 0; j < 10; j += 2) stsm_x4_t(so + trow + 1024 * j, xr[j][0], xr[j][1], xr[j + 1][0], xr[j + 1][1]);
        if (wg) asm volatile("bar.sync 2, 128;" ::: "memory"); else asm volatile("bar.sync 1, 128;" ::: "memory");
        TSTAMP2(5); CSA(13);
        if ((tid & 127) == 0) {
            fence_async_smem();
            asm volatile("cp.async.bulk.tensor.2d.global.shared::cta.bulk_group [%0, {%1, %2}], [%3];" ::"l"(&tmX1), "r"(mb * 128 + 64 * wg), "r"(hg * 80), "r"(so) : "memory");
            asm volatile("cp.async.bulk.commit_group;" ::: "memory");
        }
        __syncwarp();
        const float p0 = *(volatile const float*)&rw[g].x, p1 = *(volatile const float*)&rw[g + 8].x;
        float s[3][4] = {};
        const uint32_t pp[2] = {__byte_perm(__float_as_uint(p0), 0, 0x3232), __byte_perm(__float_as_uint(p1), 0, 0x3232)};
#pragma unroll
        for (int j = 0; j < 10; j += 2) {
            const uint32_t d0 = sub2(xr[j][0], pp[0]), d1 = sub2(xr[j][1], pp[1]), d2 = sub2(xr[j + 1][0], pp[0]), d3 = sub2(xr[j + 1][1], pp[1]);
            mma_bf16(s[0], xr[j][0], xr[j][1], xr[j + 1][0], xr[j + 1][1], 0x3f803f80u, 0x3f803f80u);
            mma_bf16(s[1], d0, d1, d2, d3, d0, d2);
            mma_bf16(s[2], d0, d1, d2, d3, d1, d3);
        }
        if (t == (g >> 1)) {
            float2* rp = rsum + ri;
            asm volatile("red.relaxed.gpu.global.add.v2.f32 [%0], {%1, %2};" ::"l"(rp), "f"(fmaf(-80.f, p0, s[0][0])), "f"((g & 1) ? s[1][1] : s[1][0]) : "memory");
            asm volatile("red.relaxed.gpu.global.add.v2.f32 [%0], {%1, %2};" ::"l"(rp + 4), "f"(fmaf(-80.f, p1, s[0][2])), "f"((g & 1) ? s[2][3] : s[2][2]) : "memory");
        }
        asm volatile("cp.async.bulk.wait_group.read 0;" ::: "memory");
        TSTAMP2(6); CSA(14); CSA_END;
        if (tid == 0) DBGC(63);
        if (tid == 128) DBGC(28);
        if (tid == 0) DBGCAL(2);
        GSTAMP(g_tim1, 14);
        SPAN(1 + 4 * layer, 3);
    }
#undef layer
}

static int h_nsm;
static void* h_sym[11];
static TileTab h_tab[2];
static CUtensorMap h_tmX0, h_tmX1, h_tmR0, h_tmR1, h_tmX1st, h_tmOut;
static KgMaps h_tmW;
typedef CUresult (*PFN_encodeTiled)(CUtensorMap*, CUtensorMapDataType, cuuint32_t, void*, const cuuint64_t*, const cuuint64_t*,
                                    const cuuint32_t*, const cuuint32_t*, CUtensorMapInterleave, CUtensorMapSwizzle,
                                    CUtensorMapL2promotion, CUtensorMapFloatOOBfill);
static void make_tmap(CUtensorMap* tm, const void* ptr, uint64_t cols, uint64_t rows, uint32_t bc, uint32_t br, CUtensorMapSwizzle sw, uint64_t pitch = 0, uint64_t hi = 0, uint32_t bh = 2) {
    static PFN_encodeTiled fn = nullptr;
    if (!fn) {
        void* p = nullptr; cudaDriverEntryPointQueryResult qr;
        cudaGetDriverEntryPoint("cuTensorMapEncodeTiled", &p, cudaEnableDefault, &qr);
        fn = (PFN_encodeTiled)p;
    }
    if (br == 0) {
        cuuint64_t dims[5] = {16, 2, rows / 8, 4, cols / 16}; cuuint64_t strides[4] = {cols * 2, cols * 16, cols * 4, 32};
        cuuint32_t box[5] = {16, 2, bc, 4, 5}; cuuint32_t es[5] = {1, 1, 1, 1, 1};
        fn(tm, CU_TENSOR_MAP_DATA_TYPE_BFLOAT16, 5, const_cast<void*>(ptr), dims, strides, box, es, CU_TENSOR_MAP_INTERLEAVE_NONE, sw,
           CU_TENSOR_MAP_L2_PROMOTION_L2_128B, CU_TENSOR_MAP_FLOAT_OOB_FILL_NONE);
        return;
    }
    if (hi == 16) {
        cuuint64_t dims[4] = {16, 32, 120, 20}; cuuint64_t strides[3] = {3840, 32, 32 * 3840};
        cuuint32_t box[4] = {16, 32, 5, 2}; cuuint32_t es[4] = {1, 1, 1, 1};
        fn(tm, CU_TENSOR_MAP_DATA_TYPE_BFLOAT16, 4, const_cast<void*>(ptr), dims, strides, box, es, CU_TENSOR_MAP_INTERLEAVE_NONE, sw,
           CU_TENSOR_MAP_L2_PROMOTION_L2_128B, CU_TENSOR_MAP_FLOAT_OOB_FILL_NONE);
        return;
    }
    if (bh == 0) {
        cuuint64_t dims[5] = {64, 64, 2, 16, 10}; cuuint64_t strides[4] = {pitch * 2, hi * 2, cols * 2, rows * 2};
        cuuint32_t box[5] = {64, 64, 2, 1, 1}; cuuint32_t es[5] = {1, 1, 1, 1, 1};
        fn(tm, CU_TENSOR_MAP_DATA_TYPE_BFLOAT16, 5, const_cast<void*>(ptr), dims, strides, box, es, CU_TENSOR_MAP_INTERLEAVE_NONE, sw,
           CU_TENSOR_MAP_L2_PROMOTION_L2_128B, CU_TENSOR_MAP_FLOAT_OOB_FILL_NONE);
        return;
    }
    if (hi) {
        cuuint64_t dims[3] = {cols, rows, hi == 64 ? 32u : 2u}; cuuint64_t strides[2] = {pitch * 2, hi * 2};
        cuuint32_t box[3] = {bc, br, bh}; cuuint32_t es[3] = {1, 1, 1};
        fn(tm, CU_TENSOR_MAP_DATA_TYPE_BFLOAT16, 3, const_cast<void*>(ptr), dims, strides, box, es, CU_TENSOR_MAP_INTERLEAVE_NONE, sw,
           CU_TENSOR_MAP_L2_PROMOTION_L2_128B, CU_TENSOR_MAP_FLOAT_OOB_FILL_NONE);
        return;
    }
    cuuint64_t dims[2] = {cols, rows}; cuuint64_t strides[1] = {(pitch ? pitch : cols) * 2};
    cuuint32_t box[2] = {bc, br}; cuuint32_t es[2] = {1, 1};
    fn(tm, CU_TENSOR_MAP_DATA_TYPE_BFLOAT16, 2, const_cast<void*>(ptr), dims, strides, box, es, CU_TENSOR_MAP_INTERLEAVE_NONE, sw,
       CU_TENSOR_MAP_L2_PROMOTION_L2_128B, CU_TENSOR_MAP_FLOAT_OOB_FILL_NONE);
}
template <typename... Args>
static void launch_pdl(void (*kern)(Args...), int grid, int block, int smem, Args... args) {
    cudaLaunchConfig_t cfg = {};
    cfg.gridDim = dim3(grid); cfg.blockDim = dim3(block); cfg.dynamicSmemBytes = smem; cfg.stream = cudaStreamPerThread;
    cudaLaunchAttribute at[1];
    at[0].id = cudaLaunchAttributeProgrammaticStreamSerialization; at[0].val.programmaticStreamSerializationAllowed = 1;
    cfg.attrs = at; cfg.numAttrs = 1;
    cudaLaunchKernelEx(&cfg, kern, args...);
}
static void launch_stage(int k, void* const* d_in, void* d_out) {
    const Par par = {k > 1 ? nullptr : (const bf16*)d_in[4], (const bf16*)d_in[5], (const bf16*)d_in[6], (const bf16*)d_in[7], (const bf16*)d_in[8], (const bf16*)d_in[9], k > 1, 0, (const bf16*)d_in[0],
                     (uint4*)h_sym[4], (uint4*)h_sym[2], (uint4*)h_sym[6], (uint4*)h_sym[3], (uint4*)h_sym[0], (float*)h_sym[5], (uint4*)h_sym[1], (const bf16*)d_in[1], (const bf16*)d_in[2]};
    auto a1 = h_nsm == 132 ? a1_kernel<true> : a1_kernel<false>;
    switch (k) {
        case 1: a1<<<h_nsm, A1_THREADS, A1_SMEM, cudaStreamPerThread>>>(par, h_tmX0, h_tmR0, h_tmX1st, h_tmW, h_tab[0]); break;
        case 3: launch_pdl(conv_kernel, DM / CV_CPB, CV_THREADS, CV_SMEM, 0, (const uint4*)h_sym[7], (const float4*)h_sym[4], (const bf16*)h_sym[8], (bf16*)h_sym[9], (const uint4*)h_sym[0], h_tmOut); break;
        case 5: launch_pdl(a1, h_nsm, A1_THREADS, A1_SMEM, par, h_tmX1, h_tmR1, h_tmX1st, h_tmW, h_tab[1]); break;
        case 7: launch_pdl(conv_kernel, DM / CV_CPB, CV_THREADS, CV_SMEM, 1, (const uint4*)h_sym[7] + SEQ / 8, (const float4*)h_sym[4] + SEQ / 2, (const bf16*)h_sym[8], (bf16*)h_sym[10], (const uint4*)h_sym[0], h_tmOut); break;
        default: break;
    }
}
static int n_stage_kernels() { return 9; }
static const char* stage_name(int k) { const char* n[] = {"kgen", "a1", "a2", "conv", "tr", "a1", "a2", "conv", "tr"}; return n[k]; }

extern "C" void kernel_launch(void* const* d_in, const int* in_sizes, int n_in, void* d_out, int out_size) {
    (void)in_sizes; (void)n_in; (void)out_size;
    static const void *p_in = nullptr, *p_w1 = nullptr, *p_w2 = nullptr, *p_out = nullptr;
    if (p_in != d_in[0] || p_w1 != d_in[1] || p_w2 != d_in[2] || p_out != d_out) {
        cudaFuncSetAttribute(conv_kernel, cudaFuncAttributeMaxDynamicSharedMemorySize, CV_SMEM);
        cudaFuncSetAttribute(a1_kernel<true>, cudaFuncAttributeMaxDynamicSharedMemorySize, A1_SMEM);
        cudaFuncSetAttribute(a1_kernel<false>, cudaFuncAttributeMaxDynamicSharedMemorySize, A1_SMEM);
        int dev; cudaGetDevice(&dev); cudaDeviceGetAttribute(&h_nsm, cudaDevAttrMultiProcessorCount, dev);
        if (h_nsm != 132) h_nsm = 128;
        cudaGetSymbolAddress(&h_sym[0], g_tap); cudaGetSymbolAddress(&h_sym[1], g_wq); cudaGetSymbolAddress(&h_sym[2], g_wo);
        cudaGetSymbolAddress(&h_sym[3], g_halo); cudaGetSymbolAddress(&h_sym[4], g_sum); cudaGetSymbolAddress(&h_sym[5], g_csp); cudaGetSymbolAddress(&h_sym[6], g_of);
        cudaGetSymbolAddress(&h_sym[7], g_piv); cudaGetSymbolAddress(&h_sym[8], g_x1T); cudaGetSymbolAddress(&h_sym[9], g_xcT); cudaGetSymbolAddress(&h_sym[10], g_yT);
        for (int i = 0; i < 264; i++) {
            const int s = i % 132, h = (s - 64) >> 1;
            const int t = h_nsm != 132 ? s : s < 64 ? ((s >> 1) & 7) * 16 + (s >> 4) * 2 + (s & 1) : s < 120 ? (1 + h % 7) * 16 + 8 + (h / 7) * 2 + (s & 1) : s < 124 ? 128 : s - 116;
            const int hg = (4 * (t >> 6) + (t & 3)) & 7;
            const uint64_t wp = (uint64_t)h_sym[1] + hg * 10 * WQ_STAGE;
            h_tab[i / 132].e[s] = make_uint4((uint32_t)wp, (uint32_t)(wp >> 32), ((t >> 2) & 15) | (i / 132) << 4 | hg << 8 | 5 * (hg >> 2) << 16 | (uint32_t)t << 24, 0);
        }
        void *px1, *px2;
        cudaGetSymbolAddress(&px1, g_x1T); cudaGetSymbolAddress(&px2, g_xcT);
        make_tmap(&h_tmX0, d_in[0], 128 * 640, 64, 64, 64, CU_TENSOR_MAP_SWIZZLE_128B, 1280, 640, 0);
        make_tmap(&h_tmX1, px2, 128, 64 * XCP, 64, 64, CU_TENSOR_MAP_SWIZZLE_128B, XCP, 64, 0);
        make_tmap(&h_tmR0, d_in[0], 640, 1024, 80, 64, CU_TENSOR_MAP_SWIZZLE_NONE, 1280, 640, 1);
        make_tmap(&h_tmR1, px2, 64, 640, 64, 80, CU_TENSOR_MAP_SWIZZLE_128B, XCP, 64, 1);
        make_tmap(&h_tmX1st, px1, 2048, 640, 64, 80, CU_TENSOR_MAP_SWIZZLE_128B, XCP);
        make_tmap(&h_tmW.q, d_in[1], 16, 640, 16, 32, CU_TENSOR_MAP_SWIZZLE_32B, 1920, 16, 5);
        make_tmap(&h_tmW.o, d_in[2], 640, 640, 4, 0, CU_TENSOR_MAP_SWIZZLE_32B);
        make_tmap(&h_tmW.t, d_in[2], 640, 640, 2, 0, CU_TENSOR_MAP_SWIZZLE_32B);
        make_tmap(&h_tmOut, d_out, 640, 1024, 80, 8, CU_TENSOR_MAP_SWIZZLE_NONE, 1280, 640, 1);
        p_in = d_in[0]; p_w1 = d_in[1]; p_w2 = d_in[2]; p_out = d_out;
    }
    for (int k = 0; k < n_stage_kernels(); k++) launch_stage(k, d_in, d_out);
}
```

```cpp
#include <cuda_runtime.h>
#include <cuda_bf16.h>
#include <cuda_fp16.h>
#include <stdint.h>
#include <cuda.h>

typedef __nv_bfloat16 bf16;

constexpr int SEQ = 2048;
constexpr int DM = 640;
constexpr int NMODE = 192;

__device__ __forceinline__ float bf2f(bf16 v) { return __bfloat162float(v); }
__device__ __forceinline__ float rbf(float v) {
    uint32_t r;
    asm("cvt.rn.bf16x2.f32 %0, %1, %2;" : "=r"(r) : "f"(v), "f"(0.f));
    return __uint_as_float(r);
}
__device__ __forceinline__ uint32_t pack2(float lo, float hi) {
    __nv_bfloat162 t = __floats2bfloat162_rn(lo, hi);
    return *reinterpret_cast<uint32_t*>(&t);
}
__device__ __forceinline__ void pdl_sync() {
    asm volatile("griddepcontrol.wait;" ::: "memory");
    asm volatile("griddepcontrol.launch_dependents;" ::: "memory");
}
__device__ __forceinline__ float sqrt_apx(float v) { float r; asm("sqrt.approx.ftz.f32 %0, %1;" : "=f"(r) : "f"(v)); return r; }
__device__ __forceinline__ float rcp_apx(float v) { float r; asm("rcp.approx.ftz.f32 %0, %1;" : "=f"(r) : "f"(v)); return r; }
__device__ __forceinline__ uint32_t smem_u32(const void* p) { return (uint32_t)__cvta_generic_to_shared(p); }

constexpr int TAPB = 2944, TAPE = 928;
__device__ __align__(128) uint4 g_tap[DM * TAPB / 16];
#define XPAD 64
constexpr int XCP = SEQ + XPAD;
__device__ __align__(128) bf16 g_x1T[DM * XCP];
__device__ __align__(128) bf16 g_xcT[DM * XCP];
__device__ __align__(128) uint4 g_of[128 * 1280];
constexpr int WQ_STAGE = 240 * 128, WOB = 80 * 160;
__device__ __align__(128) uint4 g_wq[8 * 10 * WQ_STAGE / 16];
__device__ __align__(128) uint4 g_wo[64 * WOB / 16];
__device__ __align__(128) uint4 g_xb[128 * 240];
__device__ __align__(16) float g_csp[10 * 1920];
#define KG_HG 1
#define FSTR 32
__device__ __align__(128) float2 g_sum[2 * SEQ + 256 * FSTR];
__device__ __align__(16) bf16 g_piv[2 * SEQ];
__device__ __align__(128) bf16 g_yT[DM * XCP];
__device__ uint32_t g_epoch;
__device__ __align__(16) unsigned long long g_rstat[SEQ];
__device__ __align__(128) uint4 g_halo[640 * 148];
__device__ __forceinline__ unsigned long long tagw(uint32_t payload, uint32_t tag) { return ((unsigned long long)tag << 32) | payload; }
__device__ __forceinline__ ulonglong2 ld_tag2(const ulonglong2* p) {
    ulonglong2 v;
    asm volatile("ld.relaxed.gpu.global.v2.u64 {%0, %1}, [%2];" : "=l"(v.x), "=l"(v.y) : "l"(p) : "memory");
    return v;
}
__device__ __forceinline__ bool tag_ok(ulonglong2 v, uint32_t tag) { return (uint32_t)(v.x >> 32) == tag && (uint32_t)(v.y >> 32) == tag; }
__device__ __forceinline__ uint32_t ld_epoch() { uint32_t v; asm volatile("ld.relaxed.gpu.global.u32 %0, [%1];" : "=r"(v) : "l"(&g_epoch) : "memory"); return v + 1; }
constexpr int SPIN_MAX = 1 << 20;
__device__ __align__(128) uint32_t g_started[11 * 32];
__device__ __forceinline__ void sm_started(int slot) { asm volatile("red.relaxed.gpu.global.add.u32 [%0], 1;" ::"l"(g_started + slot) : "memory"); }
__device__ __forceinline__ void publish(int slot) {
    asm volatile("fence.proxy.async.global;" ::: "memory");
    asm volatile("red.release.gpu.global.add.u32 [%0], 1;" ::"l"(g_started + slot) : "memory");
}
__device__ __forceinline__ void await_all(int slot, uint32_t want) {
#pragma unroll 1
    for (int it = 0; it < SPIN_MAX; it++) {
        uint32_t v;
        asm volatile("ld.acquire.gpu.global.u32 %0, [%1];" : "=r"(v) : "l"(g_started + slot) : "memory");
        if (__all_sync(~0u, (int)(v - want) >= 0)) break;
        __nanosleep(50);
    }
    asm volatile("fence.proxy.async.global;" ::: "memory");
}
__device__ __noinline__ void sm_idle(int slot) {
    if (threadIdx.x != 288) return;
    asm volatile("fence.acq_rel.gpu;" ::: "memory");
    asm volatile("fence.proxy.async.global;" ::: "memory");
    sm_started(slot);
    const uint32_t want = ld_epoch() * gridDim.x;
    pdl_sync();
#pragma unroll 1
    for (int it = 0; it < SPIN_MAX; it++) {
        uint32_t v;
        asm volatile("ld.relaxed.gpu.global.u32 %0, [%1];" : "=r"(v) : "l"(g_started + slot) : "memory");
        if ((int)(v - want) >= 0) break;
        __nanosleep(100);
    }
}
struct TileTab { uint4 e[132]; };
__device__ __forceinline__ bool elect() {
    uint32_t p;
    asm volatile("{\n.reg .pred p;\nelect.sync _|p, 0xffffffff;\nselp.b32 %0, 1, 0, p;\n}" : "=r"(p));
    return p;
}
#define DBG_SYMS
#define TSTAMP(i)
#define TSTAMP1(i)
#define TSTAMP1T(i, t)
#define TSTAMP1X(i, t)
#define SPAN(k, i)
#define GSTAMP(arr, i)
#define TSTAMP2(i)
#define TSTAMP3(i)
#define TSTAMP4(i)
#define TSTAMPK(i, t)
#define TSTAMPC(i)
#define DBGC(i)
#define DBGV(i, v)
#define DBGCAL(i)

#define CSK(i)
#define CSK_END
#define CSA(i)
#define CSA_END
#define CST(i)
#define CST_END
#define CST_EXTRA 0
__device__ __forceinline__ void mma_bf16(float* d, uint32_t a0, uint32_t a1, uint32_t a2, uint32_t a3, uint32_t b0, uint32_t b1) {
    asm volatile("mma.sync.aligned.m16n8k16.row.col.f32.bf16.bf16.f32 {%0,%1,%2,%3}, {%4,%5,%6,%7}, {%8,%9}, {%0,%1,%2,%3};"
                 : "+f"(d[0]), "+f"(d[1]), "+f"(d[2]), "+f"(d[3]) : "r"(a0), "r"(a1), "r"(a2), "r"(a3), "r"(b0), "r"(b1));
}
__device__ __forceinline__ void mma_bf16_k8(float* d, uint32_t a0, uint32_t a1, uint32_t b0) {
    asm volatile("mma.sync.aligned.m16n8k8.row.col.f32.bf16.bf16.f32 {%0,%1,%2,%3}, {%4,%5}, {%6}, {%0,%1,%2,%3};"
                 : "+f"(d[0]), "+f"(d[1]), "+f"(d[2]), "+f"(d[3]) : "r"(a0), "r"(a1), "r"(b0));
}
__device__ __forceinline__ void ldsm_x4(uint32_t* r, uint32_t addr) {
    asm volatile("ldmatrix.sync.aligned.m8n8.x4.shared.b16 {%0,%1,%2,%3}, [%4];"
                 : "=r"(r[0]), "=r"(r[1]), "=r"(r[2]), "=r"(r[3]) : "r"(addr));
}

__device__ __forceinline__ void ldsm_x4_t(uint32_t* r, uint32_t addr) {
    asm volatile("ldmatrix.sync.aligned.m8n8.x4.trans.shared.b16 {%0,%1,%2,%3}, [%4];"
                 : "=r"(r[0]), "=r"(r[1]), "=r"(r[2]), "=r"(r[3]) : "r"(addr));
}
__device__ __forceinline__ void mbar_init(uint32_t bar, int count) { asm volatile("mbarrier.init.shared::cta.b64 [%0], %1;" ::"r"(bar), "r"(count)); }
__device__ __forceinline__ void mbar_arrive(uint32_t bar) { asm volatile("mbarrier.arrive.shared::cta.b64 _, [%0];" ::"r"(bar) : "memory"); }
__device__ __forceinline__ void mbar_wait(uint32_t bar, uint32_t parity) {
    asm volatile("{\n.reg .pred p;\nWAIT_LOOP:\n"
                 "mbarrier.try_wait.parity.shared::cta.b64 p, [%0], %1;\n"
                 "@p bra.uni WAIT_DONE;\nbra.uni WAIT_LOOP;\nWAIT_DONE:\n}" ::"r"(bar), "r"(parity) : "memory");
}

__device__ __forceinline__ void mbar_expect_tx(uint32_t bar, uint32_t bytes) {
    asm volatile("mbarrier.arrive.expect_tx.shared::cta.b64 _, [%0], %1;" ::"r"(bar), "r"(bytes) : "memory");
}
__device__ __forceinline__ void tma_load_2d(uint32_t dst, const void* tmap, int c0, int c1, uint32_t bar) {
    asm volatile("cp.async.bulk.tensor.2d.shared::cluster.global.mbarrier::complete_tx::bytes [%0], [%1, {%3, %4}], [%2];"
                 ::"r"(dst), "l"(tmap), "r"(bar), "r"(c0), "r"(c1) : "memory");
}
__device__ __forceinline__ void tma_load_3d(uint32_t dst, const void* tmap, int c0, int c1, int c2, uint32_t bar) {
    asm volatile("cp.async.bulk.tensor.3d.shared::cluster.global.mbarrier::complete_tx::bytes [%0], [%1, {%3, %4, %5}], [%2];"
                 ::"r"(dst), "l"(tmap), "r"(bar), "r"(c0), "r"(c1), "r"(c2) : "memory");
}
__device__ __forceinline__ void fence_async_smem() { asm volatile("fence.proxy.async.shared::cta;" ::: "memory"); }
__device__ __forceinline__ void bulk_load(uint32_t dst, const void* src, uint32_t bytes, uint32_t bar) {
    asm volatile("cp.async.bulk.shared::cluster.global.mbarrier::complete_tx::bytes [%0], [%1], %2, [%3];"
                 ::"r"(dst), "l"(src), "r"(bytes), "r"(bar) : "memory");
}
__device__ __forceinline__ void stsm_x4(uint32_t addr, uint32_t r0, uint32_t r1, uint32_t r2, uint32_t r3) {
    asm volatile("stmatrix.sync.aligned.m8n8.x4.shared.b16 [%0], {%1,%2,%3,%4};" ::"r"(addr), "r"(r0), "r"(r1), "r"(r2), "r"(r3) : "memory");
}
__device__ __forceinline__ void stsm_x4_t(uint32_t addr, uint32_t r0, uint32_t r1, uint32_t r2, uint32_t r3) {
    asm volatile("stmatrix.sync.aligned.m8n8.x4.trans.shared.b16 [%0], {%1,%2,%3,%4};" ::"r"(addr), "r"(r0), "r"(r1), "r"(r2), "r"(r3) : "memory");
}
__device__ __forceinline__ void prefetch_tmap(const void* tmap) { asm volatile("prefetch.tensormap [%0];" ::"l"(tmap) : "memory"); }

__device__ __forceinline__ float2 cexp_at(float wr2, float wi, float p) {
    float er;
    asm("ex2.approx.ftz.f32 %0, %1;" : "=f"(er) : "f"(wr2 * p));
    float th = wi * p;
    const float k = rintf(th * 0.15915494309189535f);
    th = fmaf(k, -6.2831854820251465f, th);
    th = fmaf(k, 1.7484555314695172e-7f, th);
    return make_float2(er * __cosf(th), er * __sinf(th));
}
__device__ __forceinline__ float2 cmul(float2 a, float2 b) {
    return make_float2(fmaf(a.x, b.x, -a.y * b.y), fmaf(a.x, b.y, a.y * b.x));
}
__device__ __forceinline__ float2 csqr(float2 a) { return make_float2(fmaf(a.x, a.x, -a.y * a.y), (a.x + a.x) * a.y); }
__device__ __forceinline__ uint32_t packh(float2 v) {
    uint32_t r;
    asm("cvt.rn.f16x2.f32 %0, %1, %2;" : "=r"(r) : "f"(v.y), "f"(v.x));
    return r;
}
__device__ __forceinline__ uint2 packr(float2 v) { return make_uint2(packh(v), packh(make_float2(-v.y, v.x))); }
__device__ __forceinline__ uint32_t hcmul(uint32_t a, uint2 b) {
    const __half2 x = *reinterpret_cast<const __half2*>(&a);
    const __half2 r = __hfma2(__high2half2(x), *reinterpret_cast<const __half2*>(&b.y), __hmul2(__low2half2(x), *reinterpret_cast<const __half2*>(&b.x)));
    return *reinterpret_cast<const uint32_t*>(&r);
}

struct Par { const bf16 *logA, *Aim, *Cre, *Cim, *logdt, *dsk; int layer, pad; const bf16* x; uint4 *sum, *wop, *of, *halo, *tap; float* csp; uint4* wq; const bf16 *wqkv, *wo; };
struct KgMaps { CUtensorMap q, o, t; };

__device__ __forceinline__ void bulk_prefetch(const void* p, uint32_t bytes) { asm volatile("cp.async.bulk.prefetch.L2.global [%0], %1;" ::"l"(p), "r"(bytes) : "memory"); }
__device__ __forceinline__ void bulk_store(void* dst, uint32_t src, uint32_t bytes) { asm volatile("cp.async.bulk.global.shared::cta.bulk_group [%0], [%1], %2;" ::"l"(dst), "r"(src), "r"(bytes) : "memory"); }
__device__ __forceinline__ void kgen_first(const Par& in, const KgMaps& tm, const uint32_t b0, const uint32_t wbar, const bool one) {
    const uint32_t blk = blockIdx.x, sec = (blk >= 40) + (blk >= 80), it = (blk >> 3) - 5 * sec, up = (blk >> 2) & 1, hi = blk >> 6;
    auto fetch = [&](int h) {
        if (blk < 120) asm volatile("cp.async.bulk.tensor.4d.shared::cluster.global.mbarrier::complete_tx::bytes [%0], [%1, {%3, %3, %4, %5}], [%2];"
                                    ::"r"(b0 + 10240 * h), "l"(&tm.q), "r"(wbar + 8 * h), "r"(0), "r"(sec * 40 + (blk & 7) * 5), "r"(2 * it + 10 * (up ^ h)) : "memory");
    };
    auto fetch_o = [&](int i) {
        asm volatile("cp.async.bulk.tensor.5d.shared::cluster.global.mbarrier::complete_tx::bytes [%0], [%1, {%3, %3, %4, %3, %5}], [%2];"
                     ::"r"(b0 + 20480 + i * 5120), "l"(&tm.o + i), "r"(wbar + 16), "r"(0), "r"((blk & 7) * 10 + (hi + i) * 4), "r"(((blk >> 3) & 7) * 5) : "memory");
    };
    if (one) {
#pragma unroll
        for (int i = 0; i < 3; i++) mbar_init(wbar + 8 * i, 1);
        asm volatile("fence.mbarrier_init.release.cluster;" ::: "memory");
        fetch(0);
    }
    __syncwarp();
    if (blk >> 20) __trap();
    if (one) {
        bulk_prefetch(in.wqkv + blk * 9600, 19200);
        fetch(1);
        bulk_prefetch(in.wo + blk * 3200, 6400);
        fetch_o(0);
        if (hi) fetch_o(1);
        mbar_expect_tx(wbar, 10240); mbar_expect_tx(wbar + 8, 10240); mbar_expect_tx(wbar + 16, 5120 + hi * 2560);
        bulk_prefetch(in.x + blk * 10240, 20480);
    }
}
__device__ __forceinline__ void kgen_side(const Par& in, const uint32_t b0, const uint32_t wbar) {
    const uint32_t blk = blockIdx.x, sec = (blk >= 40) + (blk >= 80), it = (blk >> 3) - 5 * sec, cg = (blk >> 3) & 7, hb = blk & 7;
    unsigned char* dst = reinterpret_cast<unsigned char*>(in.wq) + (hb * 10 + it) * WQ_STAGE + sec * 5120;
    if (blk < 120) {
        mbar_wait(wbar, 0);
        CSK(2);
        bulk_store(dst, b0, 5120); bulk_store(dst + 15360, b0 + 5120, 5120);
        mbar_wait(wbar + 8, 0);
        CSK(3);
        bulk_store(dst + 5 * WQ_STAGE, b0 + 10240, 5120); bulk_store(dst + 5 * WQ_STAGE + 15360, b0 + 15360, 5120);
        asm volatile("cp.async.bulk.commit_group;" ::: "memory");
        asm volatile("cp.async.bulk.wait_group 0;" ::: "memory");
        CSK(4);
        publish(96 + 32 * KG_HG * hb);
        CSK(5);
    }
    if (blk < 128) {
        mbar_wait(wbar + 16, 0);
        bulk_store(reinterpret_cast<unsigned char*>(in.wop) + (cg * 8 + (hb == cg ? 0 : hb + (hb < cg))) * WOB + (blk >> 6) * 5120, b0 + 20480, blk < 64 ? 5120 : 7680);
        asm volatile("cp.async.bulk.commit_group;" ::: "memory");
    }
}
__device__ __forceinline__ void kgen_sums(const Par& in, const uint32_t b0, const int h) {
    const int lane = threadIdx.x & 31, blk = blockIdx.x;
    if (blk < 120) {
        float cs[5][4] = {};
#pragma unroll
        for (int a = 0; a < 4; a++)
#pragma unroll
            for (int j = 0; j < 5; j++) {
                uint32_t w[4];
                ldsm_x4_t(w, b0 + h * 10240 + j * 1024 + ((lane >> 4) * 8 + (lane & 7)) * 32 + ((((lane >> 3) ^ (lane >> 2)) & 1) << 4) + (a >> 1) * 5120 + (a & 1) * 512);
                mma_bf16(cs[j], w[0], w[1], w[2], w[3], 0x3f803f80u, 0x3f803f80u);
            }
#pragma unroll
        for (int j = 0; j < 5; j++)
            if ((lane & 3) < 2) in.csp[(blk + 120 * h) * 80 + j * 16 + (lane >> 2) + 8 * (lane & 3)] = (lane & 3) ? cs[j][2] : cs[j][0];
    }
}
struct KgPar { uint32_t pw[4], ph[4], pdt, pdsk; };
__device__ __forceinline__ void kgen_load(const Par& in, const bf16* logA, const int w11, KgPar& k) {
    const uint32_t o = blockIdx.x * 480 + min(w11 * 48, w11 * 32 + 128), ow = o + (threadIdx.x & 31), oh = o + ow + (w11 < 8 ? 64 : 0);
    k.pdt = reinterpret_cast<const unsigned short*>(in.logdt)[ow / 96];
    k.pdsk = reinterpret_cast<const unsigned short*>(in.dsk)[ow / 96];
#pragma unroll
    for (int i = 0; i < 4; i++) {
        const bf16* p = i == 0 ? logA : i == 1 ? in.Aim : i == 2 ? in.Cre : in.Cim;
        k.pw[i] = reinterpret_cast<const uint32_t*>(p)[ow]; k.ph[i] = reinterpret_cast<const unsigned short*>(p)[oh];
    }
}
__device__ __forceinline__ void kgen_tables(const Par& in, uint4* tabs, const int w11, const KgPar& kp) {
    const int lane = threadIdx.x & 31, grp = min(w11 >> 1, 4), warp = w11 - 2 * grp;
    const int blk = blockIdx.x, d = blk * 5 + grp, tid = warp * 32 + lane;
    uint4* tab = tabs + grp * (2 * 256);
    const uint32_t *pw = kp.pw, *ph = kp.ph;
#pragma unroll
    for (int i = 0; i < 3; i++)
        if (i < 2 || w11 * 32 + lane < 36) asm volatile("st.global.v4.u32 [%0], {%1,%1,%1,%1};" ::"l"(in.halo + blk * 740 + w11 * 32 + lane + 352 * i), "r"(~0u));
    __syncwarp();
    if (w11 == 10) {
        if (lane < 16) in.sum[blk * 16 + lane] = make_uint4(0, 0, 0, 0);
        else if (lane < 20) reinterpret_cast<uint32_t*>(in.sum + 2048)[(blk * 4 + lane - 16) * FSTR] = 0;
    } else if (w11 > 1) asm volatile("bar.arrive 9, 352;" ::: "memory");
#pragma unroll
    for (int i = 0; i < 6; i++) tabs[w11 * 256 + 32 * i + lane] = make_uint4(0, 0, 0, 0);
    __syncwarp();
    CSK(1);
    const uint32_t tw = smem_u32(tabs) + w11 * 4096;
    const int g = lane >> 2, t = lane & 3;
    const int mt = lane >> 3, r = lane & 7;
    const uint32_t st1 = tw + mt * 1024 + r * 16, st2 = tw + (mt & 1) * 1024 + (mt >> 1) * 128 + ((r ^ (mt >> 1)) << 4), st3 = tw + 2048 + mt * 128 + ((r ^ mt) << 4);
    const uint32_t lda = tw + (mt & 1) * 1024 + r * 128 + (((mt >> 1) ^ r) << 4), ldb = tw + (mt >> 1) * 1024 + r * 128 + (((mt & 1) ^ r) << 4), ldc = tw + 2048 + r * 128 + ((mt ^ r) << 4);
    auto ldsm = [](uint32_t* v, uint32_t a) {
        asm volatile("ldmatrix.sync.aligned.m8n8.x4.shared.b16 {%0,%1,%2,%3}, [%4];" : "=r"(v[0]), "=r"(v[1]), "=r"(v[2]), "=r"(v[3]) : "r"(a) : "memory");
    };
    auto mma = [](float* c, const uint32_t* a, const uint32_t* b) {
        asm("mma.sync.aligned.m16n8k16.row.col.f32.f16.f16.f32 {%0,%1,%2,%3}, {%4,%5,%6,%7}, {%8,%9}, {%0,%1,%2,%3};"
            : "+f"(c[0]), "+f"(c[1]), "+f"(c[2]), "+f"(c[3]) : "r"(a[0]), "r"(a[1]), "r"(a[2]), "r"(a[3]), "r"(b[0]), "r"(b[1]));
    };
    asm volatile("st.shared.u32 [%0], %1;" ::"r"(tw + 3072), "r"(st1 ^ st2 ^ st3 ^ lda ^ ldb ^ ldc) : "memory");
    if (in.pad) __trap();
    const float dt = rbf(expf(__uint_as_float(kp.pdt << 16)));
    const uint32_t cm = __vmaxu2(__vmaxu2(pw[2] & 0x7fff7fffu, pw[3] & 0x7fff7fffu), __byte_perm(ph[2], ph[3], 0x5410) & 0x7fff7fffu);
    const int ex = min(max((int)(__float_as_uint(__uint_as_float(__reduce_max_sync(~0u, max(cm << 16, cm & 0xffff0000u))) * dt) >> 23), 20), 240);
    const float scale = __uint_as_float((uint32_t)(127 + 10 + 127 - ex) << 23), unscale = 2.0f * __uint_as_float((uint32_t)(ex - 10) << 23);
    float k2048 = 0.f;
    float acc[5][4] = {};
    uint32_t af[4][4] = {};
    auto rest = [&] {
        uint32_t b[4][4], c[8];
#pragma unroll
        for (int k = 0; k < 4; k++) {
            ldsm(b[k], ldb ^ (k << 5));
            if (!(k & 1)) ldsm(c + 2 * k, ldc ^ (k << 5));
        }
#pragma unroll
        for (int k = 0; k < 4; k++) { mma(acc[2], af[k], b[k]); mma(acc[3], af[k], b[k] + 2); mma(acc[4], af[k], c + 2 * k); }
    };
#pragma unroll 1
    for (uint32_t sel = 0x1076; sel < (grp < 4 ? 0x6000u : 0x4000u); sel += 0x2200) {
        rest();
        auto par = [&](int i) { return __uint_as_float(__byte_perm(pw[i], ph[i], sel)); };
        const float wr2 = -rbf(expf(par(0))) * dt * 1.4426950408889634f, wi = par(1) * dt;
        const float2 y1 = cexp_at(wr2, -wi, 1.f), w64 = cexp_at(wr2, wi, 64.f), y4 = csqr(csqr(y1)), z8 = csqr(make_float2(y4.x, -y4.y)), y128 = csqr(make_float2(w64.x, -w64.y));
        float2 h0 = make_float2(1.f, 0.f), g0 = make_float2(par(2) * dt * scale, -par(3) * dt * scale);
        const float2 v2 = csqr(y128), v3 = cmul(v2, y128), v4 = csqr(v2), v8 = csqr(v4), c8 = cmul(g0, v8);
        const uint2 z64 = packr(w64), v[8] = {make_uint2(packh(c8), 0u), packr(y128), packr(v2), packr(v3), packr(v4), packr(cmul(v4, y128)), packr(csqr(v3)), packr(cmul(v4, v3))};
        k2048 += fmaf(c8.x, v8.x, -c8.y * v8.y);
        uint32_t ge[4];
#pragma unroll
        for (int e = 0; e < 8; e++) {
            const uint32_t p = packh(h0), q = packh(g0);
            if (!(e & 1)) ge[e >> 1] = q;
            stsm_x4((st1 ^ (e << 4)) + e * 128, p, e ? hcmul(p, z64) : z64.x, q, hcmul(q, v[1]));
            if (e < 7) { h0 = e ? cmul(h0, z8) : z8; g0 = cmul(g0, y1); }
        }
        __syncwarp();
        uint32_t b[4][4];
#pragma unroll
        for (int k = 0; k < 4; k++) { ldsm(af[k], lda ^ (k << 5)); ldsm(b[k], (ldb ^ (k << 5)) + 2048); }
#pragma unroll
        for (int e = 0; e < 8; e += 2) {
            stsm_x4((st2 ^ (e << 4)) + e * 128, hcmul(ge[e & 3], v[2 + (e >> 2)]), hcmul(ge[0], v[4 + (e >> 1)]), hcmul(ge[(e & 3) + 1], v[2 + (e >> 2)]), hcmul(ge[2], v[4 + (e >> 1)]));
            if (!(e & 3)) stsm_x4((st3 ^ (e << 4)) + e * 128, e ? hcmul(v[0].x, v[e]) : v[0].x, hcmul(v[0].x, v[e + 1]), hcmul(v[0].x, v[e + 2]), hcmul(v[0].x, v[e + 3]));
            mma(acc[0], af[e >> 1], b[e >> 1]);
            mma(acc[1], af[e >> 1], b[e >> 1] + 2);
        }
        __syncwarp();
        if (sel == 0x1076) CSK(3);
    }
    rest();
#pragma unroll
    for (int e = 0; e < 5; e++) k2048 += __shfl_xor_sync(~0u, k2048, 1 << e);
    {
        float* Pp = reinterpret_cast<float*>(tab + warp * 256);
        auto sw = [](int i) { return i ^ ((i >> 2) & 24); };
#pragma unroll
        for (int h = 0; h < 2; h++) {
            const int b = g + 8 * h;
            *reinterpret_cast<float2*>(Pp + sw(8 * b + 2 * t)) = make_float2(acc[0][2 * h] * unscale, acc[0][2 * h + 1] * unscale);
            *reinterpret_cast<float2*>(Pp + 128 + sw(8 * b + 2 * t)) = make_float2(acc[1][2 * h] * unscale, acc[1][2 * h + 1] * unscale);
            *reinterpret_cast<float2*>(Pp + 256 + sw(4 * b + 2 * (t & 1) + 64 * (t >> 1))) = make_float2(acc[2][2 * h] * unscale, acc[2][2 * h + 1] * unscale);
            *reinterpret_cast<float2*>(Pp + 384 + sw(2 * b + 32 * t)) = make_float2(acc[3][2 * h] * unscale, acc[3][2 * h + 1] * unscale);
            Pp[512 + sw(b + 32 * t)] = acc[4][2 * h] * unscale;
            Pp[512 + sw(b + 32 * t + 16)] = acc[4][2 * h + 1] * unscale;
        }
        if (lane == 0) Pp[640] = k2048 * unscale;
    }
    CSK(4);
    asm volatile("bar.sync %0, %1;" ::"r"(grp + 4), "r"(grp < 4 ? 64 : 96) : "memory");
    if (warp == 2) return;
    const float* Kp = reinterpret_cast<const float*>(tab);
    auto ksum = [&](int i) -> float { return rbf(Kp[i] + Kp[1024 + i] + (grp < 4 ? 0.f : Kp[2048 + i])); };
    auto ksum2 = [&](int q) -> float2 {
        q ^= (q >> 2) & 12;
        const float2 a = reinterpret_cast<const float2*>(Kp)[q], b = reinterpret_cast<const float2*>(Kp)[512 + q];
        const float2 c = grp < 4 ? make_float2(0.f, 0.f) : reinterpret_cast<const float2*>(Kp)[1024 + q];
        return make_float2(a.x + b.x + c.x, a.y + b.y + c.y);
    };
    {
        uint2* W2 = reinterpret_cast<uint2*>(in.tap + d * (TAPB / 16)) + 8;
        uint2* E4 = W2 + (TAPE - 64) / 8;
        float2 v = ksum2(64 * warp + lane), z = ksum2(64 * warp + 32 + lane), y = ksum2(128 + tid);
        const int q = (96 + tid) ^ (((96 + tid) >> 2) & 6);
        const float4 ua = reinterpret_cast<const float4*>(Kp)[q], uc = reinterpret_cast<const float4*>(Kp)[256 + q], ud = grp < 4 ? make_float4(0.f, 0.f, 0.f, 0.f) : reinterpret_cast<const float4*>(Kp)[512 + q];
        const float4 ub = make_float4(uc.x + ud.x, uc.y + ud.y, uc.z + ud.z, uc.w + ud.w);
        const float s1 = ksum(tid == 31 ? 336 : lane ? 384 : 103), s2 = ksum(tid == 31 ? 512 : tid ? 640 : 231);
        if (tid == 0) v.x += __uint_as_float(kp.pdsk << 16);
        if (tid == 63) y.y -= s1;
        const uint32_t lo = pack2(v.x, v.y), hi = pack2(z.x, z.y), tp = pack2(y.x, y.y);
        uint32_t nl = __shfl_sync(~0u, lo, lane - 1), nh = __shfl_sync(~0u, lane == 31 ? lo : hi, lane - 1), nt = __shfl_sync(~0u, tp, lane + 1);
        if (lane == 0) nl = warp ? __float_as_uint(s1) : 0u;
        if (lane == 31) nt = warp ? 0u : __float_as_uint(s1) >> 16;
        W2[64 * warp + lane] = make_uint2(__byte_perm(lo, nl, 0x7610), __byte_perm(lo, 0, 0x1032));
        W2[64 * warp + lane + 32] = make_uint2(__byte_perm(hi, nh, 0x7610), __byte_perm(hi, 0, 0x1032));
        reinterpret_cast<uint4*>(W2)[64 + tid] = make_uint4(__byte_perm(tp, __float_as_uint(s2), tid ? 0x1010 : 0x7610), __byte_perm(tp, 0, 0x1010), __byte_perm(tp, 0, 0x1032), __byte_perm(nt, tp, 0x7610));
        E4[(tid < 32 ? 159 : 209 - 32) + tid] = make_uint2(pack2(ua.x + ub.x, ua.y + ub.y), pack2(ua.z + ub.z, ua.w + ub.w - (tid == 31 ? s2 : 0.f)));
        if (tid == 63) E4[241] = make_uint2(__float_as_uint(s2) >> 16, 0u);
    }
    CSK(5);
    SPAN(0, 3);
}

#define CV_SLEEP 40
#define CV_LD "ld.relaxed.gpu.global"
#define CV_NL 1
#define CV_D2 3
#define CV_PDH 12
#define CV_PDF 4
#define CV_HAND 7
constexpr int CV_CPB = 5;
constexpr int CV_THREADS = 512;
constexpr int UPADF = 128;
constexpr int ULEN = UPADF + SEQ;
constexpr int XLEN = XCP;
constexpr int BX_5 = 0, BX_3 = 3264, BX_9 = 6528, BX_7 = 8960, BX_LEN = 11392;
constexpr int CV_SM_U = 0;
constexpr int CV_SM_T = CV_CPB * ULEN * 2;
constexpr int CV_SM_B = CV_SM_T + CV_CPB * TAPB;
constexpr int CV_SM_X = CV_SM_B + CV_CPB * BX_LEN;
constexpr int CV_SM_Y = (CV_SM_X + CV_CPB * XLEN * 2 + 127) & ~127;
constexpr int CV_SM_CNT = CV_SM_Y + CV_CPB * 8192;
constexpr int CV_SM_O = CV_SM_CNT + 128;
constexpr int CV_SMEM = CV_SM_O + 20480 + CST_EXTRA;
static_assert(ULEN % 128 == 0 && CV_SM_B % 128 == 0 && CV_SM_CNT % 128 == 0, "layout");

__device__ __forceinline__ uint32_t sub2(uint32_t x, uint32_t m) {
    const __nv_bfloat162 d = __hsub2(*reinterpret_cast<const __nv_bfloat162*>(&x), *reinterpret_cast<const __nv_bfloat162*>(&m));
    return *reinterpret_cast<const uint32_t*>(&d);
}
__device__ __forceinline__ uint32_t add2(uint32_t x, uint32_t y) {
    const __nv_bfloat162 d = __hadd2_rn(*reinterpret_cast<const __nv_bfloat162*>(&x), *reinterpret_cast<const __nv_bfloat162*>(&y));
    return *reinterpret_cast<const uint32_t*>(&d);
}
__device__ __forceinline__ void wgmma_fence() { asm volatile("wgmma.fence.sync.aligned;" ::: "memory"); }
__device__ __forceinline__ void wgmma_commit() { asm volatile("wgmma.commit_group.sync.aligned;" ::: "memory"); }
template <int N> __device__ __forceinline__ void wgmma_wait() { asm volatile("wgmma.wait_group.sync.aligned %0;" ::"n"(N) : "memory"); }
__device__ __forceinline__ uint64_t make_desc(uint32_t addr, uint32_t lbo, uint32_t sbo, uint32_t mode) {
    return (uint64_t)((addr & 0x3FFFF) >> 4) | ((uint64_t)(lbo >> 4) << 16) | ((uint64_t)(sbo >> 4) << 32) | ((uint64_t)mode << 62);
}
__device__ __forceinline__ void wgmma_rs128(float (&d)[64], uint2 hi, uint2 lo, uint64_t db, int acc) {
    asm volatile("{\n.reg .pred p;\nsetp.ne.b32 p, %69, 0;\nwgmma.mma_async.sync.aligned.m64n128k16.f32.bf16.bf16 {%0,%1,%2,%3,%4,%5,%6,%7,%8,%9,%10,%11,%12,%13,%14,%15,%16,%17,%18,%19,%20,%21,%22,%23,%24,%25,%26,%27,%28,%29,%30,%31,%32,%33,%34,%35,%36,%37,%38,%39,%40,%41,%42,%43,%44,%45,%46,%47,%48,%49,%50,%51,%52,%53,%54,%55,%56,%57,%58,%59,%60,%61,%62,%63}, {%64,%65,%66,%67}, %68, p, 1, 1, 0;\n}"
                 : "+f"(d[0]), "+f"(d[1]), "+f"(d[2]), "+f"(d[3]), "+f"(d[4]), "+f"(d[5]), "+f"(d[6]), "+f"(d[7]), "+f"(d[8]), "+f"(d[9]), "+f"(d[10]), "+f"(d[11]), "+f"(d[12]), "+f"(d[13]), "+f"(d[14]), "+f"(d[15]), "+f"(d[16]), "+f"(d[17]), "+f"(d[18]), "+f"(d[19]), "+f"(d[20]), "+f"(d[21]), "+f"(d[22]), "+f"(d[23]), "+f"(d[24]), "+f"(d[25]), "+f"(d[26]), "+f"(d[27]), "+f"(d[28]), "+f"(d[29]), "+f"(d[30]), "+f"(d[31]), "+f"(d[32]), "+f"(d[33]), "+f"(d[34]), "+f"(d[35]), "+f"(d[36]), "+f"(d[37]), "+f"(d[38]), "+f"(d[39]), "+f"(d[40]), "+f"(d[41]), "+f"(d[42]), "+f"(d[43]), "+f"(d[44]), "+f"(d[45]), "+f"(d[46]), "+f"(d[47]), "+f"(d[48]), "+f"(d[49]), "+f"(d[50]), "+f"(d[51]), "+f"(d[52]), "+f"(d[53]), "+f"(d[54]), "+f"(d[55]), "+f"(d[56]), "+f"(d[57]), "+f"(d[58]), "+f"(d[59]), "+f"(d[60]), "+f"(d[61]), "+f"(d[62]), "+f"(d[63])
                 : "r"(hi.x), "r"(hi.y), "r"(lo.x), "r"(lo.y), "l"(db), "r"(acc));
}
template <int V> struct Int { __device__ constexpr operator int() const { return V; } };
__device__ __forceinline__ void sts4(uint32_t a, const uint32_t* v) { asm volatile("st.shared.v4.u32 [%0], {%1,%2,%3,%4};" ::"r"(a), "r"(v[0]), "r"(v[1]), "r"(v[2]), "r"(v[3]) : "memory"); }
__device__ __forceinline__ uint32_t lds1(uint32_t a) { uint32_t v; asm volatile("ld.shared.u32 %0, [%1];" : "=r"(v) : "r"(a) : "memory"); return v; }
__device__ __forceinline__ uint32_t lds1v(uint32_t a) { uint32_t v; asm volatile("ld.volatile.shared.u32 %0, [%1];" : "=r"(v) : "r"(a) : "memory"); return v; }
__device__ __forceinline__ uint4 lds4(uint32_t a) { uint4 v; asm volatile("ld.shared.v4.u32 {%0,%1,%2,%3}, [%4];" : "=r"(v.x), "=r"(v.y), "=r"(v.z), "=r"(v.w) : "r"(a) : "memory"); return v; }
__device__ __forceinline__ uint4 ldx(uint32_t a) {
    uint4 v;
    asm volatile("ld.shared.v2.u32 {%0,%1}, [%4];\nld.shared.v2.u32 {%2,%3}, [%4+128];" : "=r"(v.x), "=r"(v.y), "=r"(v.z), "=r"(v.w) : "r"(a) : "memory");
    return v;
}
__device__ __forceinline__ void cv_store(unsigned char* p, uint4 x, uint4 y) {
    asm volatile("st.relaxed.gpu.global.v2.u32 [%0], {%1,%2};" ::"l"(p), "r"(add2(x.x, __byte_perm(y.x, y.y, 0x5410))), "r"(add2(x.y, __byte_perm(y.z, y.w, 0x5410))) : "memory");
    asm volatile("st.relaxed.gpu.global.v2.u32 [%0], {%1,%2};" ::"l"(p + 128), "r"(add2(x.z, __byte_perm(y.x, y.y, 0x7632))), "r"(add2(x.w, __byte_perm(y.z, y.w, 0x7632))) : "memory");
}
__device__ __forceinline__ int usw(int ch) { return ch ^ ((ch >> 3) & 1); }
__global__ void __launch_bounds__(CV_THREADS, 1) conv_kernel(int layer, const uint4* __restrict__ piv, const float4* __restrict__ sum, const bf16* __restrict__ x1T,
                                                             bf16* __restrict__ dst, const uint4* __restrict__ tap, const __grid_constant__ CUtensorMap tmOut) {
    extern __shared__ __align__(1024) unsigned char sm[];
    SPAN(3 + 4 * layer, 0);
    bf16* Us = reinterpret_cast<bf16*>(sm + CV_SM_U);
    bf16* Xs = reinterpret_cast<bf16*>(sm + CV_SM_X);
#define CV_IDX int tid; asm volatile("mov.u32 %0, %tid.x;" : "=r"(tid)); const int lane = tid & 31, warp = __shfl_sync(~0u, tid >> 5, 0);
    const int d0 = blockIdx.x * CV_CPB, tile = blockIdx.x; (void)tile;
    const uint32_t cnt = smem_u32(sm + CV_SM_CNT);
    struct Lc { uint32_t a4, a8, uc, ud, y, e4, en, sp, ss; int go; };
    auto lane_consts = [&](int lane, int c) {
        const int mat = lane >> 3, r = lane & 7, g = lane >> 2, ti = lane & 3, e = g - 2 * ti;
        const int j2 = 13 + (r ^ 1) + 8 * (mat >> 1), j3 = j2 + 2, i0 = 8 * (mat & 1);
        const uint32_t sb = smem_u32(sm), oc = sb + usw(16 * (mat >> 1) + 2 * r + (mat & 1)) * 16;
        const Lc l = {sb + CV_SM_B + c * BX_LEN + ((j2 & 1) ? BX_3 + (4 * j2 + i0 + 84) * 2 : BX_5 + (4 * j2 + i0 + 80) * 2),
                      sb + CV_SM_B + c * BX_LEN + ((j3 & 1) ? BX_7 : BX_9) + (8 * j3 + i0 + 136) * 2,
                      oc + CV_SM_U + (c * ULEN + UPADF) * 2, sb + CV_SM_U + (c * ULEN + UPADF) * 2 + usw(16 * mat + 2 * r + 2) * 16, oc + CV_SM_Y + c * 8192,
                      sb + CV_SM_T + c * TAPB + TAPE + (307 + 2 * g - ti) * 4, sb + CV_SM_T + c * TAPB + (528 + e) * 4,
                      e == -5 ? 0x4410u : e == -4 ? 0x1044u : 0x4444u, e == 3 ? 0x4410u : e == 4 ? 0x1044u : 0x4444u,
                      c * XCP * 2 + (lane >> 4) * 256 + (lane & 15) * 8};
        asm volatile("st.shared.u32 [%0], %1;" ::"r"(sb + CV_SM_CNT + 120), "r"(l.y ^ l.a4 ^ l.a8 ^ l.uc ^ l.ud ^ l.e4 ^ l.en ^ l.sp ^ l.ss ^ l.go) : "memory");
        return l;
    };
    unsigned char* const dq = reinterpret_cast<unsigned char*>(dst + (size_t)d0 * XCP);
    auto far = [&](auto T0_, const auto& seq, const Lc& lc, int c, int lane, const uint2 (&f)[20], uint32_t kk) {
        constexpr int T0 = T0_, T1 = T0 + 6, TC = T0 > 7 ? T0 : 7, NS = sizeof(seq) / sizeof(seq[0]), PD = T0 > 7 ? CV_PDH : CV_PDF;
        uint32_t bq[28], yw[4], yz[4], P, S;
        uint4 xv, yv;
        asm("prmt.b32 %0, %1, 0, %2;" : "=r"(P) : "r"(kk), "r"(lc.sp));
        asm("prmt.b32 %0, %1, 0, %2;" : "=r"(S) : "r"(kk), "r"(lc.ss));
#pragma unroll
        for (int k = 0; 2 * k < T1 - TC + 4; k++) ldsm_x4(bq + 4 * k, lc.uc + (TC - 8) * 256 + 512 * k);
#pragma unroll
        for (int k = 0; 4 * k < T1 - TC; k++) ldsm_x4(bq + 20 + 4 * k, lc.ud + (TC - 8) * 256 + 1024 * k);
        CST(3);
        mbar_wait(cnt + 8 * c, 0);
        mbar_wait(cnt + 40, 0);
        CST(4);
        float acc[6][4] = {};
        uint32_t a[PD + 1][4];
#pragma unroll
        for (int i = -PD; i < NS + 3; i++) {
            if (i + PD < NS) ldsm_x4_t(a[(i + PD) % (PD + 1)], seq[i + PD] < 32 ? lc.a4 + (seq[i + PD] - 2) * 128 : lc.a8 + (seq[i + PD] - 34) * 256);
            if (i < 0) continue;
#pragma unroll
            for (int T = T0; T < T1; T++) {
                if (i >= NS) break;
                const int ee = seq[i] < 32 ? 2 * T - 6 - seq[i] : T + 35 - seq[i];
                if (i == 0 && T >= TC) mma_bf16(acc[T - T0], P, 0u, S, P, bq[2 * (T - TC)], bq[2 * (T - TC) + 1]);
                if (i == 1 && T >= TC) mma_bf16_k8(acc[T - T0], 0u, S, bq[20 + T - TC]);
                if (i == (T >= TC ? 2 : 0)) mma_bf16(acc[T - T0], f[19].x, 0u, f[19].y, f[19].x, bq[2 * (T - TC + 4)], bq[2 * (T - TC + 4) + 1]);
                if (seq[i] < 32 ? ee >= 0 && ee <= 9 : ee >= 10) mma_bf16(acc[T - T0], a[i % (PD + 1)][0], a[i % (PD + 1)][1], a[i % (PD + 1)][2], a[i % (PD + 1)][3], f[ee].x, f[ee].y);
            }
#pragma unroll
            for (int k = 0; k < 3; k++) {
                const int o = 256 * T0 + 512 * k;
                auto at = [&](int d) { return i - d >= 0 && i - d < NS && seq[i - d < 0 ? 0 : i - d < NS ? i - d : 0] == 2 * T0 + 4 * k - 4; };
                if (at(CV_D2)) {
                    cv_store(dq + lc.go + o, xv, yv);
                    if (layer > 19 - 2 * k) __trap();
                }
                if (at(-2)) { ldsm_x4_t(yw, lc.y + o); ldsm_x4_t(yz, lc.y + 3584 + o); }
                if (at(1)) {
#pragma unroll
                    for (int q = 0; q < 4; q++) yw[q] = add2(add2(yw[q], yz[q]), pack2(acc[2 * k + (q >> 1)][2 * (q & 1)], acc[2 * k + (q >> 1)][2 * (q & 1) + 1]));
                    stsm_x4_t(lc.y + o, yw[0], yw[1], yw[2], yw[3]);
                    xv = ldx(smem_u32(Xs) + lc.go + o);
                    __syncwarp();
                    yv = lds4(smem_u32(sm + CV_SM_Y) + c * 8192 + o + usw(lane) * 16);
                    if (layer > 20 - 2 * k) __trap();
                    if (k == 2) CST(6);
                }
            }
        }
    };
    TSTAMP1X(9, 256);
    if (threadIdx.x >= 256) {
        if (threadIdx.x < 288 && elect()) {
            mbar_init(cnt + 48, 1);
            asm volatile("fence.mbarrier_init.release.cluster;" ::: "memory");
            bulk_load(smem_u32(sm + CV_SM_T), tap + d0 * (TAPB / 16), CV_CPB * TAPB, cnt + 48);
            mbar_expect_tx(cnt + 48, CV_CPB * TAPB);
        }
        CV_IDX
        const int wgu = (warp >> 2) & 1, g = lane >> 2, ti = lane & 3;
        CST(1);
        if (warp > 8 && elect()) {
            if (warp < 15) mbar_init(cnt + 8 * (warp - 9), warp == 14 ? 8 : 4);
            else if (layer) prefetch_tmap(&tmOut);
        }
        if (warp < 13 && lane < 17 - (warp == 12)) {
            const int off = warp == 12 ? CV_SM_U : CV_SM_B + (warp == 11 ? BX_7 : (warp - 8) * BX_3), str = warp == 12 ? ULEN * 2 : BX_LEN;
#pragma unroll
            for (int c = 0; c < CV_CPB; c++) *reinterpret_cast<uint4*>(sm + off + c * str + 16 * lane) = make_uint4(0, 0, 0, 0);
        }
        fence_async_smem();
        asm volatile("bar.arrive 3, 512;" ::: "memory");
        asm volatile("bar.sync 1, 256;" ::: "memory");
        TSTAMP1X(10, 256);
        asm volatile("setmaxnreg.inc.sync.aligned.u32 168;");
        const uint32_t Tc = smem_u32(sm + CV_SM_T) + (16 + 128 * (warp & 2) + 8 * (warp & 1) + g - 2 * ti) * 4;
        uint2 fa[8][2], fn[8][2];
        auto near_taps = [&](uint2 (&f)[8][2], int c) {
#pragma unroll
            for (int m = 0; m < 16; m++) f[m >> 1][m & 1] = make_uint2(lds1v(Tc + c * TAPB + 64 * (m >> 1) - 32 * (m & 1)), lds1v(Tc + c * TAPB + 64 * (m >> 1) - 32 * (m & 1) + 512));
        };
        CST(6);
        mbar_wait(cnt + 48, 0);
        TSTAMP1X(11, 256); CST(5);
        near_taps(fa, 3 * wgu);
        near_taps(fn, 2 - wgu);
        const int hc = wgu ? warp & 3 : 4;
        const Lc lc = lane_consts(lane, hc);
        TSTAMP1X(12, 256); CST(0);
        uint32_t ya = smem_u32(sm + CV_SM_Y) + wgu * 8192 + (warp & 2) * 2048 + usw(2 * lane + (warp & 1)) * 16;
        uint64_t db = make_desc(smem_u32(Us + wgu * ULEN + UPADF), 16, 256, 3);
        if (wgu) { asm volatile("bar.sync 6, 384;" ::: "memory"); fence_async_smem(); }
        int c = wgu;
        auto chain = [&](const uint2 (&f)[8][2], auto&& meanwhile) {
            float acc[64];
            asm volatile("bar.sync %0, %1;" ::"r"(c ? 4 + wgu : 2), "r"(c ? 256 : 384) : "memory");
            TSTAMPC(1 + 3 * c);
            if (c < 2) CST(7);
            if (c == 0) fence_async_smem();
            wgmma_fence();
#pragma unroll
            for (int m = 0; m < 8; m++) {
                wgmma_rs128(acc, f[m][0], f[m][1], db - (uint64_t)(2 * m), m);
                if (m == CV_HAND && c < 4) asm volatile("bar.arrive %0, 256;" ::"r"(5 - wgu) : "memory");
            }
            wgmma_commit();
            asm volatile("griddepcontrol.launch_dependents;" ::: "memory");
            TSTAMPC(2 + 3 * c); CST(13 + (c >> 1));
            meanwhile();
            wgmma_wait<0>();
            TSTAMPC(3 + 3 * c); CST(10 + (c >> 1));
            uint32_t w[16];
#pragma unroll
            for (int j = 0; j < 16; j++) w[j] = j ? pack2(acc[4 * j] + acc[4 * j - 2], acc[4 * j + 1] + acc[4 * j - 1]) : pack2(acc[0], acc[1]);
#pragma unroll
            for (int j = 0; j < 16; j += 4) stsm_x4_t(ya + 256 * j, w[j], w[j + 1], w[j + 2], w[j + 3]);
            __syncwarp();
            if (lane == 0) mbar_arrive(cnt + 8 * c);
            c += 2; ya += 16384; db += ULEN / 4;
        };
        const uint32_t e4 = lc.e4, e8 = e4 + 428 - 4 * g;
        uint2 fl[4];
        uint32_t kk;
#pragma unroll 1
        for (;;) {
            if (c != 1) chain(fa, [&] {
                if (c == 3 || warp + c == 12) {
#pragma unroll
                    for (int k = 0; k < 19; k++) (k < 16 ? fn[(k >> 1) & 7][k & 1] : fl[k & 3]) = make_uint2(lds1(k < 10 ? e4 + 32 * k + 16 : e8 + 32 * k - 304), lds1(k < 10 ? e4 + 32 * k : e8 + 32 * k - 320));
                    fl[3] = make_uint2(lds1(lc.en), lds1(lc.en - 32));
                    kk = lds1(smem_u32(sm + CV_SM_T) + TAPB * hc + TAPE + 1672);
                }
            });
            if (c > 4) break;
            if (c == 2) { asm volatile("bar.sync 7, 384;" ::: "memory"); fence_async_smem(); }
            chain(fn, [&] { if (c == 2) near_taps(fa, 4); });
        }
        TSTAMP1X(6, 256); CST(2);
        if (wgu || warp == 8) {
            constexpr int seq[29] = {5, 6, 32, 7, 33, 8, 34, 9, 35, 10, 36, 11, 12, 13, 14, 15, 16, 17, 37, 18, 38, 19, 20, 21, 39, 22, 40, 23, 24};
            uint2 f[20];
#pragma unroll
            for (int k = 0; k < 20; k++) f[k] = k < 16 ? fn[(k >> 1) & 7][k & 1] : fl[k & 3];
            far(Int<10>(), seq, lc, hc, lane, f, kk);
        }
    } else {
        asm volatile("setmaxnreg.dec.sync.aligned.u32 88;");
        CV_IDX
        CST(5);
        const uint4* ppv = piv + tid;
        const float4* psv = sum + tid;
        const uint2* pxv = reinterpret_cast<const uint2*>(x1T + (size_t)d0 * XCP) + (tid >> 4) * 32 + (tid & 15);
        asm volatile("st.shared.u64 [%0], %1;" ::"r"(smem_u32(sm + CV_SM_O) + tid * 16), "l"((uint64_t)ppv ^ (uint64_t)psv ^ (uint64_t)pxv) : "memory");
        const int tc = (0x04302100 >> (4 * warp)) & 7;
        const Lc lc = lane_consts(lane, tc);
        pdl_sync();
        SPAN(3 + 4 * layer, 1);
        TSTAMP(0); CST(0);
        if (tid == 0) TSTAMPC(0);
        if (threadIdx.x == 0) { GSTAMP(g_tim, 15); }
        float4 sv[4];
        uint4 pv;
#pragma unroll
        for (int k = 0; k < 4; k++)
            asm volatile(CV_LD ".v4.f32 {%0,%1,%2,%3}, [%4];" : "=f"(sv[k].x), "=f"(sv[k].y), "=f"(sv[k].z), "=f"(sv[k].w) : "l"(psv + 256 * k) : "memory");
        asm volatile(CV_LD ".v4.u32 {%0,%1,%2,%3}, [%4];" : "=r"(pv.x), "=r"(pv.y), "=r"(pv.z), "=r"(pv.w) : "l"(ppv) : "memory");
        uint2 xe[CV_CPB], xo[CV_CPB];
#pragma unroll
        for (int c = 0; c < CV_NL; c++) {
            asm volatile(CV_LD ".v2.u32 {%0,%1}, [%2];" : "=r"(xe[c].x), "=r"(xe[c].y) : "l"(pxv + c * (XCP / 4)) : "memory");
            asm volatile(CV_LD ".v2.u32 {%0,%1}, [%2];" : "=r"(xo[c].x), "=r"(xo[c].y) : "l"(pxv + c * (XCP / 4) + 16) : "memory");
        }
#define CV_XD 300
#define CV_XW 0
        if (warp == CV_XW) {
            if (elect()) {
                const uint32_t c0 = clock();
                mbar_init(cnt + 56, 1);
                asm volatile("fence.mbarrier_init.release.cluster;" ::: "memory");
                mbar_expect_tx(cnt + 56, CV_CPB * 4096);
                while (clock() - c0 < CV_XD) ;
#pragma unroll
                for (int c = CV_NL; c < CV_CPB + CV_NL; c++) bulk_load(smem_u32(Xs + (c % CV_CPB) * XLEN), x1T + (size_t)(d0 + c % CV_CPB) * XCP, 4096, cnt + 56);
            }
            __syncwarp();
            CST(15);
        }
        constexpr float idm = 1.0f / DM;
        uint32_t mw[4];
        float rs[8];
#pragma unroll
        for (int k = 0; k < 4; k++) {
            const uint32_t pw = k == 0 ? pv.x : k == 1 ? pv.y : k == 2 ? pv.z : pv.w;
            mw[k] = pack2(fmaf(sv[k].x, idm, __uint_as_float(pw << 16)), fmaf(sv[k].z, idm, __uint_as_float(pw & 0xffff0000u)));
            uint32_t vr;
            asm("cvt.rn.relu.bf16x2.f32 %0, %1, %2;" : "=r"(vr) : "f"(fmaf(sv[k].z * -idm, sv[k].z, sv[k].w) * idm), "f"(fmaf(sv[k].x * -idm, sv[k].x, sv[k].y) * idm));
            const uint32_t ve = pack2(__uint_as_float(vr << 16) + 1e-5f, __uint_as_float(vr & 0xffff0000u) + 1e-5f);
            const uint32_t sd = pack2(sqrt_apx(__uint_as_float(ve << 16)), sqrt_apx(__uint_as_float(ve & 0xffff0000u)));
            rs[2 * k] = rcp_apx(__uint_as_float(sd << 16)); rs[2 * k + 1] = rcp_apx(__uint_as_float(sd & 0xffff0000u));
        }
        if (rs[0] != 123.f) TSTAMP(13);
        const uint32_t ua = smem_u32(Us) + usw(tid + UPADF / 8) * 16;
        uint32_t uw[CV_CPB][4];
#pragma unroll
        for (int c = 0; c < CV_CPB; c++) {
            if (c == CV_NL) {
                if (warp == CV_XW) { mbar_wait(cnt + 56, 0); CST(7); }
                asm volatile("bar.sync 10, 256;" ::: "memory");
            }
            if (c == 1 || c == 2) {
#pragma unroll
                for (int k = c; k < (c == 1 ? 2 : CV_CPB); k++) {
 const uint4 v = ldx(smem_u32(Xs + k * XLEN) + (tid >> 4) * 256 + (tid & 15) * 8); xe[k] = make_uint2(v.x, v.y); xo[k] = make_uint2(v.z, v.w); }
            }
            const uint32_t e0 = sub2(xe[c].x, mw[0]), e1 = sub2(xe[c].y, mw[1]), o0 = sub2(xo[c].x, mw[2]), o1 = sub2(xo[c].y, mw[3]);
            uw[c][0] = pack2(__uint_as_float(e0 << 16) * rs[0], __uint_as_float(o0 << 16) * rs[4]); uw[c][1] = pack2(__uint_as_float(e0 & 0xffff0000u) * rs[1], __uint_as_float(o0 & 0xffff0000u) * rs[5]);
            uw[c][2] = pack2(__uint_as_float(e1 << 16) * rs[2], __uint_as_float(o1 << 16) * rs[6]); uw[c][3] = pack2(__uint_as_float(e1 & 0xffff0000u) * rs[3], __uint_as_float(o1 & 0xffff0000u) * rs[7]);
            asm volatile("st.shared.v4.u32 [%0], {%1,%2,%3,%4};" ::"r"(ua + c * ULEN * 2), "r"(uw[c][0]), "r"(uw[c][1]), "r"(uw[c][2]), "r"(uw[c][3]) : "memory");
            if (c < 2) {
                asm volatile("bar.arrive %0, 384;" ::"r"(2 + 4 * c) : "memory");
                if (layer > 29 - c) __trap();
                CST(11 + c);
            }
        }
        asm volatile("bar.arrive 7, 384;" ::: "memory");
        asm volatile("bar.sync 3, 512;" ::: "memory");
        TSTAMP(1); CST(1);
        {
            auto box = [&](auto c0, auto c1, int chunk, int cb, bool full) {
                const uint32_t ea = smem_u32(Us + cb * ULEN) + usw(chunk + UPADF / 8 + (lane ? 1 : -1)) * 16, bx = smem_u32(sm + CV_SM_B + cb * BX_LEN) + chunk * 16;
                uint32_t lo[CV_CPB][4], hi[CV_CPB][2];
#pragma unroll
                for (int c = c0; c < c1; c++) {
                    lo[c][0] = 0;
#pragma unroll
                    for (int k = 1; k < 4; k++) lo[c][k] = __shfl_up_sync(~0u, uw[c][k], 1);
#pragma unroll
                    for (int k = 0; k < 2; k++) hi[c][k] = __shfl_down_sync(~0u, uw[c][k], 1);
                }
#pragma unroll
                for (int c = c0; c < c1; c++)
                    asm volatile("{\n.reg .pred p, q;\nsetp.eq.s32 p, %7, 0;\nsetp.eq.s32 q, %7, 31;\n@p ld.shared.v4.u32 {%0,%1,%2,%3}, [%6];\n@q ld.shared.v2.u32 {%4,%5}, [%6];\n}"
                                 : "+r"(lo[c][0]), "+r"(lo[c][1]), "+r"(lo[c][2]), "+r"(lo[c][3]), "+r"(hi[c][0]), "+r"(hi[c][1]) : "r"(ea + c * ULEN * 2), "r"(lane) : "memory");
#pragma unroll
                for (int c = c0; c < c1; c++) {
                    const uint32_t e[9] = {lo[c][1], lo[c][2], lo[c][3], uw[c][0], uw[c][1], uw[c][2], uw[c][3], hi[c][0], hi[c][1]};
                    uint32_t o[8], p[8], t[7], b3[5], b5[7];
#pragma unroll
                    for (int i = 0; i < 8; i++) { o[i] = __byte_perm(e[i], e[i + 1], 0x5432); p[i] = add2(e[i], o[i]); }
#pragma unroll
                    for (int i = 0; i < 5; i++) b3[i] = add2(o[i], p[i + 1]);
                    sts4(bx + c * BX_LEN + BX_3 + 160, b3);
#pragma unroll
                    for (int i = 1; i < 7; i++) { t[i] = add2(p[i], p[i + 1]); b5[i] = add2(t[i], e[i + 2]); }
                    sts4(bx + c * BX_LEN + BX_5 + 160, b5 + 2);
                    if (full) {
#pragma unroll
                        for (int i = 1; i < 5; i++) { b3[i] = add2(b3[i], t[i + 2]); t[i] = add2(t[i], b5[i + 2]); }
                        sts4(bx + c * BX_LEN + BX_7 + 272, b3 + 1);
                        sts4(bx + c * BX_LEN + BX_9 + 272, t + 1);
                    }
                }
            };
            auto reload = [&](int c, uint32_t a) { const uint4 v = lds4(a); uw[c][0] = v.x; uw[c][1] = v.y; uw[c][2] = v.z; uw[c][3] = v.w; };
            if (warp >= 6) {
#pragma unroll
                for (int c = 0; c < 3; c++) reload(c, ua - 1024 + (c + 2) * ULEN * 2);
            }
            if (warp >= 4) {
#pragma unroll
                for (int c = 3; c < 5; c++) reload(c, ua - 2048 + c * ULEN * 2);
            }
            box(Int<0>(), Int<3>(), warp < 6 ? tid : tid - 64, warp < 6 ? 0 : 2, warp < 4);
            if (warp >= 4) box(Int<3>(), Int<5>(), tid - 128, 0, true);
            else if (tid >= 128 - CV_CPB) {
                const int c = 127 - tid;
                const uint2 v = *reinterpret_cast<const uint2*>(Us + c * ULEN + UPADF);
                const float s1 = __uint_as_float(v.x << 16), s2 = s1 + __uint_as_float(v.x & 0xffff0000u), s3 = s2 + __uint_as_float(v.y << 16), s4 = s3 + __uint_as_float(v.y & 0xffff0000u);
                unsigned char* bc = sm + CV_SM_B + c * BX_LEN;
                *reinterpret_cast<uint32_t*>(bc + BX_5 + 156) = pack2(s1, s2);
                *reinterpret_cast<uint2*>(bc + BX_7 + 264) = make_uint2(v.x << 16, pack2(s2, s3));
                *reinterpret_cast<uint2*>(bc + BX_9 + 264) = make_uint2(pack2(s1, s2), pack2(s3, s4));
            }
        }
        __syncwarp();
        if (lane == 0) mbar_arrive(cnt + 40);
        TSTAMP(2); CST(2);
        if (layer && blockIdx.x == 0 && tid == 224) g_epoch = ld_epoch();
        __syncwarp();
        if ((0x6e >> warp) & 1) {
            constexpr int seq[16] = {0, 1, 2, 3, 4, 5, 6, 32, 7, 8, 9, 33, 10, 34, 11, 12};
            uint2 f[20];
            mbar_wait(cnt, 0);
            const uint32_t e8 = lc.e4 + 428 - (lane & 28);
#pragma unroll
            for (int k = 0; k < 13; k++) f[k] = make_uint2(lds1(k < 10 ? lc.e4 + 32 * k + 16 : e8 + 32 * k - 304), lds1(k < 10 ? lc.e4 + 32 * k : e8 + 32 * k - 320));
            f[19] = make_uint2(lds1(lc.en), lds1(lc.en - 32));
            far(Int<4>(), seq, lc, tc, lane, f, lds1(smem_u32(sm + CV_SM_T) + TAPB * tc + TAPE + 1672));
        }
    }
    {
        CV_IDX
        if ((0xc91 >> warp) & 1) {
            const int c = __popc(0xc91 & ((1 << warp) - 1));
            uint4 xv[2], yv[2];
#pragma unroll
            for (int k = 0; k < 2; k++) xv[k] = ldx(smem_u32(Xs + c * XLEN) + 512 * k + (lane >> 4) * 256 + (lane & 15) * 8);
            const uint32_t u0 = lds1(smem_u32(Us + c * ULEN) + (lane == 31 ? UPADF * 2 : 0));
            mbar_wait(cnt + 8 * c, 0);
#pragma unroll
            for (int k = 0; k < 2; k++) yv[k] = lds4(smem_u32(sm + CV_SM_Y) + c * 8192 + 512 * k + usw(lane) * 16);
            const uint4 yz = lds4(smem_u32(sm + CV_SM_Y) + c * 8192 + 4096 + usw(lane) * 16);
            const float kk = __uint_as_float(lds1(smem_u32(sm + CV_SM_T) + TAPB * c + TAPE + 1272) << 16);
            yv[1].x = add2(yv[1].x, yz.x); yv[1].y = add2(yv[1].y, yz.y); yv[1].z = add2(yv[1].z, yz.z);
            yv[1].w = pack2(fmaf(kk, __uint_as_float(u0 << 16), __uint_as_float(yv[1].w << 16) + __uint_as_float(yz.w << 16)),
                            fmaf(kk, __uint_as_float(u0 << 16) + __uint_as_float(u0 & 0xffff0000u), __uint_as_float(yv[1].w & 0xffff0000u) + __uint_as_float(yz.w & 0xffff0000u)));
#pragma unroll
            for (int k = 0; k < 2; k++) cv_store(dq + c * XCP * 2 + (lane >> 4) * 256 + (lane & 15) * 8 + 512 * k, xv[k], yv[k]);
        }
        TSTAMP(4); CST(8);
        if (layer == 1) {
            const int rb = (blockIdx.x >> 3) + (warp & 8) * 2, cg = blockIdx.x & 7, ch = (tid >> 3) & 31;
            const bf16* src = dst + (size_t)(cg * 80 + ch) * XCP + rb * 64 + (tid & 7) * 8;
            uint32_t v[3][4];
            __syncthreads();
            if (warp & 8) { const uint32_t c0 = clock(); while (clock() - c0 < 300) ; }
            uint32_t todo = (warp & 4) ? 3 : 7;
#pragma unroll 1
            for (int it = 0; it < SPIN_MAX; it++) {
#pragma unroll
                for (int k = 0; k < 3; k++)
                    if (todo >> k & 1)
                        asm volatile("ld.relaxed.gpu.global.v4.u32 {%0,%1,%2,%3}, [%4];" : "=r"(v[k][0]), "=r"(v[k][1]), "=r"(v[k][2]), "=r"(v[k][3]) : "l"(src + k * (32 * XCP)) : "memory");
#pragma unroll
                for (int k = 0; k < 3; k++)
                    if ((todo >> k & 1) && v[k][0] != ~0u && v[k][1] != ~0u && v[k][2] != ~0u && v[k][3] != ~0u) {
                        *reinterpret_cast<uint4*>(sm + (32 * k + ch) * 272 + ((tid & 7) + (warp & 8)) * 16) = make_uint4(v[k][0], v[k][1], v[k][2], v[k][3]);
                        todo ^= 1u << k;
                    }
                if (!todo) break;
                __nanosleep(CV_SLEEP);
            }
            __syncwarp();
            asm volatile("bar.sync %0, 256;" ::"r"(8 + (warp >> 3)) : "memory");
            uint32_t w[12];
#pragma unroll
            for (int k = 0; k < 3; k++) ldsm_x4(&w[4 * k], smem_u32(sm) + min(32 * k + lane, 79) * 272 + warp * 16);
            const uint32_t ot = smem_u32(sm + CV_SM_O) + warp * 1280, oa = ot + (lane & 7) * 160 + (lane >> 3) * 16;
            stsm_x4_t(oa, w[0], w[1], w[2], w[3]);
            stsm_x4_t(oa + 64, w[4], w[5], w[6], w[7]);
            asm volatile("stmatrix.sync.aligned.m8n8.x2.trans.shared.b16 [%0], {%1,%2};" ::"r"(oa + 128), "r"(w[8]), "r"(w[9]) : "memory");
            fence_async_smem();
            __syncwarp();
            if (lane == 0) {
                asm volatile("cp.async.bulk.tensor.3d.global.shared::cta.bulk_group [%0, {%1, %2, %3}], [%4];" ::"l"(&tmOut), "r"(cg * 80), "r"((rb >> 1) * 64 + 8 * (warp & 7)), "r"(rb & 1), "r"(ot) : "memory");
                asm volatile("cp.async.bulk.commit_group;" ::: "memory");
                asm volatile("cp.async.bulk.wait_group.read 0;" ::: "memory");
            }
        }
    }
    TSTAMP(3); CST(9); CST_END;
    GSTAMP(g_tim, 14);
    SPAN(3 + 4 * layer, 3);
}

template <int TA, int TB>
__device__ __forceinline__ void wgmma_n240(float (&d)[120], uint64_t da, uint64_t db, int acc) {
    asm volatile("{\n.reg .pred p;\nsetp.ne.b32 p, %124, 0;\nwgmma.mma_async.sync.aligned.m64n240k16.f32.bf16.bf16 {%0,%1,%2,%3,%4,%5,%6,%7,%8,%9,%10,%11,%12,%13,%14,%15,%16,%17,%18,%19,%20,%21,%22,%23,%24,%25,%26,%27,%28,%29,%30,%31,%32,%33,%34,%35,%36,%37,%38,%39,%40,%41,%42,%43,%44,%45,%46,%47,%48,%49,%50,%51,%52,%53,%54,%55,%56,%57,%58,%59,%60,%61,%62,%63,%64,%65,%66,%67,%68,%69,%70,%71,%72,%73,%74,%75,%76,%77,%78,%79,%80,%81,%82,%83,%84,%85,%86,%87,%88,%89,%90,%91,%92,%93,%94,%95,%96,%97,%98,%99,%100,%101,%102,%103,%104,%105,%106,%107,%108,%109,%110,%111,%112,%113,%114,%115,%116,%117,%118,%119}, %120, %121, p, 1, 1, %122, %123;\n}"
                 : "+f"(d[0]), "+f"(d[1]), "+f"(d[2]), "+f"(d[3]), "+f"(d[4]), "+f"(d[5]), "+f"(d[6]), "+f"(d[7]), "+f"(d[8]), "+f"(d[9]), "+f"(d[10]), "+f"(d[11]), "+f"(d[12]), "+f"(d[13]), "+f"(d[14]), "+f"(d[15]), "+f"(d[16]), "+f"(d[17]), "+f"(d[18]), "+f"(d[19]), "+f"(d[20]), "+f"(d[21]), "+f"(d[22]), "+f"(d[23]), "+f"(d[24]), "+f"(d[25]), "+f"(d[26]), "+f"(d[27]), "+f"(d[28]), "+f"(d[29]), "+f"(d[30]), "+f"(d[31]), "+f"(d[32]), "+f"(d[33]), "+f"(d[34]), "+f"(d[35]), "+f"(d[36]), "+f"(d[37]), "+f"(d[38]), "+f"(d[39]), "+f"(d[40]), "+f"(d[41]), "+f"(d[42]), "+f"(d[43]), "+f"(d[44]), "+f"(d[45]), "+f"(d[46]), "+f"(d[47]), "+f"(d[48]), "+f"(d[49]), "+f"(d[50]), "+f"(d[51]), "+f"(d[52]), "+f"(d[53]), "+f"(d[54]), "+f"(d[55]), "+f"(d[56]), "+f"(d[57]), "+f"(d[58]), "+f"(d[59]), "+f"(d[60]), "+f"(d[61]), "+f"(d[62]), "+f"(d[63]), "+f"(d[64]), "+f"(d[65]), "+f"(d[66]), "+f"(d[67]), "+f"(d[68]), "+f"(d[69]), "+f"(d[70]), "+f"(d[71]), "+f"(d[72]), "+f"(d[73]), "+f"(d[74]), "+f"(d[75]), "+f"(d[76]), "+f"(d[77]), "+f"(d[78]), "+f"(d[79]), "+f"(d[80]), "+f"(d[81]), "+f"(d[82]), "+f"(d[83]), "+f"(d[84]), "+f"(d[85]), "+f"(d[86]), "+f"(d[87]), "+f"(d[88]), "+f"(d[89]), "+f"(d[90]), "+f"(d[91]), "+f"(d[92]), "+f"(d[93]), "+f"(d[94]), "+f"(d[95]), "+f"(d[96]), "+f"(d[97]), "+f"(d[98]), "+f"(d[99]), "+f"(d[100]), "+f"(d[101]), "+f"(d[102]), "+f"(d[103]), "+f"(d[104]), "+f"(d[105]), "+f"(d[106]), "+f"(d[107]), "+f"(d[108]), "+f"(d[109]), "+f"(d[110]), "+f"(d[111]), "+f"(d[112]), "+f"(d[113]), "+f"(d[114]), "+f"(d[115]), "+f"(d[116]), "+f"(d[117]), "+f"(d[118]), "+f"(d[119])
                 : "l"(da), "l"(db), "n"(TA), "n"(TB), "r"(acc));
}

__device__ __forceinline__ void wgmma_n80(float (&d)[40], uint64_t da, uint64_t db, int acc) {
    asm volatile("{\n.reg .pred p;\nsetp.ne.b32 p, %42, 0;\nwgmma.mma_async.sync.aligned.m64n80k16.f32.bf16.bf16 {%0,%1,%2,%3,%4,%5,%6,%7,%8,%9,%10,%11,%12,%13,%14,%15,%16,%17,%18,%19,%20,%21,%22,%23,%24,%25,%26,%27,%28,%29,%30,%31,%32,%33,%34,%35,%36,%37,%38,%39}, %40, %41, p, 1, 1, 0, 1;\n}"
                 : "+f"(d[0]), "+f"(d[1]), "+f"(d[2]), "+f"(d[3]), "+f"(d[4]), "+f"(d[5]), "+f"(d[6]), "+f"(d[7]), "+f"(d[8]), "+f"(d[9]), "+f"(d[10]), "+f"(d[11]), "+f"(d[12]), "+f"(d[13]), "+f"(d[14]), "+f"(d[15]), "+f"(d[16]), "+f"(d[17]), "+f"(d[18]), "+f"(d[19]), "+f"(d[20]), "+f"(d[21]), "+f"(d[22]), "+f"(d[23]), "+f"(d[24]), "+f"(d[25]), "+f"(d[26]), "+f"(d[27]), "+f"(d[28]), "+f"(d[29]), "+f"(d[30]), "+f"(d[31]), "+f"(d[32]), "+f"(d[33]), "+f"(d[34]), "+f"(d[35]), "+f"(d[36]), "+f"(d[37]), "+f"(d[38]), "+f"(d[39])
                 : "l"(da), "l"(db), "r"(acc));
}

constexpr int A1_THREADS = 384;
constexpr int A1_NST = 4;
#define A1_SKEW 8
constexpr int A1_STAGE = 16384 + WQ_STAGE;
constexpr int A1_KVP = 336;
constexpr int A1_SM_KV = 2 * A1_STAGE;
constexpr int A1_SM_END = A1_NST * A1_STAGE;
constexpr int A1_SM_BAR = A1_SM_END + 3072 + 3 * WOB + 64;
constexpr int A1_SM_RS = A1_SM_END + 512;
constexpr int A1_SM_W0 = A1_SM_END + 3072, A1_SM_W3 = A1_SM_END - 3 * WOB, A1_SM_A1 = 2 * WOB, A1_SM_A0 = A1_SM_A1 + 61440;
constexpr int A1_SM_XA = A1_SM_W0 + 2 * WOB, A1_SM_XB = A1_SM_XA + 2048;
constexpr int A1_SMEM = A1_SM_BAR + 512 + 7 * CST_EXTRA / 4;
static_assert(A1_SM_W3 >= A1_SM_KV + 144 * A1_KVP && A1_SM_W3 % 512 == 0 && A1_SM_A1 % 1024 == 0 && A1_SM_A0 <= A1_SM_KV && A1_SM_A0 + 61440 <= A1_SM_W3 && A1_SMEM <= 232448 && 11 * 4096 <= A1_STAGE, "layout");
__device__ __forceinline__ constexpr uint32_t wo_off(int h) { return h * WOB + (h < 3 ? A1_SM_W0 : h < 6 ? A1_SM_W3 - 3 * WOB : -6 * WOB); }
#define A1_FRED "red.relaxed.gpu.global.add.u32"
#define A1_FLD "ld.acquire.gpu.global.u32"
#define ST_SLEEP 20
#define ST_SLEEP0 300
#define WO_LATE bar_done
#define A1_P0 2
#define A1_PW (kb - 2)
#define A1_FSPIN SPIN_MAX
#define A1_FSLEEP 40
#define YT_LAYER 1
#define WOT 352
#define A1_WOAT 6

template <int L>
__device__ __forceinline__ void a1_mainloop(float (&acc)[120], uint32_t sbase, uint32_t bars, int wg, int tile) {
    constexpr int layer = L; (void)layer;
    const uint64_t da0 = L ? make_desc(sbase + wg * 8192, 8192, 1024, 1) : make_desc(sbase + wg * 8192, 16, 1024, 1), db0 = make_desc(sbase + 16384, 1024, 256, 3);
#pragma unroll 1
    for (int t = 0;; t++) {
        const int st = t % A1_NST;
        mbar_wait(bars + 8 * st, (t / A1_NST) & 1);
        if (t == A1_SKEW && wg == 0) mbar_wait(bars + 160, 0);
        TSTAMP3(1 + t);
        if (t == 0) CSA(0);
        wgmma_fence();
#pragma unroll
        for (int kk = 0; kk < 4; kk++) wgmma_n240<L, 1>(acc, da0 + (uint32_t)(st * (A1_STAGE / 16) + kk * (L ? 128 : 2)), db0 + (uint32_t)(st * (A1_STAGE / 16) + (kk >> 1) * (WQ_STAGE / 32) + (kk & 1) * 32), kk ? 1 : t);
        wgmma_commit();
        if (t == 9) break;
        if (t == A1_SKEW - 1 && wg == 0) wgmma_wait<0>(); else wgmma_wait<1>();
        if (t > 0 && (threadIdx.x & 127) == 0) {
            if (t != A1_SKEW || wg) mbar_arrive(bars + 8 * (A1_NST + (t - 1) % A1_NST));
            if (t == A1_SKEW - 1 && wg == 0) mbar_arrive(bars + 8 * (A1_NST + t % A1_NST));
        }
    }
}

template <bool MAP>
__global__ void __launch_bounds__(A1_THREADS, 1) a1_kernel(const __grid_constant__ Par in, const __grid_constant__ CUtensorMap tmX, const __grid_constant__ CUtensorMap tmR,
                                                           const __grid_constant__ CUtensorMap tmX1, const __grid_constant__ KgMaps tmW, const __grid_constant__ TileTab tab) {
#define layer in.layer
    const unsigned char* const wo = reinterpret_cast<const unsigned char*>(in.wop);
    float2* const rsum = reinterpret_cast<float2*>(in.sum);
    uint4* const of = in.of;
    extern __shared__ __align__(1024) unsigned char stg[];
    const uint32_t sbase = smem_u32(stg);
    const uint32_t bars = sbase + A1_SM_BAR;
    const uint32_t bar_stat = bars + 64, bar_kv = bars + 72, bar_rd = bars + 168;
    const uint32_t bar_wo = bars + 208, bar_done = bars + 216, bar_pv = bars + 224, bar_kvf = bars + 232, bar_f2 = bars + 248, bar_e2 = bars + 384, que = bars + 448;
    const int tid = threadIdx.x;
    CSK(0);
    const int w = __shfl_sync(~0u, tid >> 5, 0), wg = w >> 2;
    uint32_t smid;
    asm volatile("mov.u32 %0, %smid;" : "=r"(smid));
    const uint4 tv = tab.e[(MAP ? smid : blockIdx.x) + (tid & (smid >> 12))];
    const uint64_t pa = reinterpret_cast<const uint64_t*>(&in)[tid & (smid >> 12)], pb = reinterpret_cast<const uint64_t*>(&in)[6 + (tid & (smid >> 12))];
    const bool one = elect();
    uint32_t tz;
    const unsigned char* wq;
    auto entry = [&] { tz = __shfl_sync(~0u, tv.z, 0); wq = (const unsigned char*)(((uint64_t)__shfl_sync(~0u, tv.y, 0) << 32) | __shfl_sync(~0u, tv.x, 0)); };
    auto issue_w = [&](unsigned it) { bulk_load(sbase + (it % A1_NST) * A1_STAGE + 16384, wq + it * WQ_STAGE, WQ_STAGE, bars + 8 * (it % A1_NST)); };
    auto issue_x = [&](unsigned it, int kb) {
        asm volatile("cp.async.bulk.tensor.5d.shared::cluster.global.mbarrier::complete_tx::bytes [%0], [%1, {%3, %3, %3, %4, %5}], [%2];"
                     ::"r"(sbase + (it % A1_NST) * A1_STAGE), "l"(&tmX), "r"(bars + 8 * (it % A1_NST)), "r"(0), "r"(tz & 15), "r"(kb) : "memory");
    };
    auto first_x = [&] {
        issue_x(0, (tz >> 16) & 7); issue_x(1, ((tz >> 16) & 7) + 1);
    };
    auto expect = [&] {
#pragma unroll
        for (int i = 0; i < A1_NST; i++) mbar_expect_tx(bars + 8 * i, A1_STAGE);
    };
    if (w == 8) {
        if (one) {
            prefetch_tmap(&tmX); prefetch_tmap(&tmW.q);
#pragma unroll
            for (int i = 0; i < A1_NST; i++) mbar_init(bars + 8 * i, 1);
            asm volatile("fence.mbarrier_init.release.cluster;" ::: "memory");
        }
        __syncwarp();
        asm volatile("bar.arrive 0, 384;" ::: "memory");
        if (smid >> 12) __trap();
        entry();
        if ((tz & 0x80000010u) == 16) {
            if (one) {
                issue_w(0);
                asm volatile("griddepcontrol.wait;" ::: "memory");
                first_x();
                issue_w(1);
                expect();
                asm volatile("griddepcontrol.launch_dependents;" ::: "memory");
            }
#pragma unroll
            for (int kb = 2; kb < A1_NST; kb++) {
                __syncwarp();
                mbar_wait(bars + 8 * (kb - 2), 0);
                if (one) { issue_x(kb, ((tz >> 16) & 7) + kb); issue_w(kb); }
                CSK(6 + kb);
            }
        }
        __syncwarp();
        if (!(tz & 16) && blockIdx.x < 128) kgen_first(in, tmW, sbase + A1_SM_W0, bars - 24, one);
        __syncwarp();
    }
    if (w > 8) CSK(8);
    const bool gen = w != 8 && in.logA && blockIdx.x < 128;
    KgPar kp;
    const int w11 = w < 8 ? 2 * (w & 3) + (w >> 2) : w - 1;
    if (gen) kgen_load(in, reinterpret_cast<const bf16*>(pa), w11, kp);
    if (w > 8) CSK(9);
    if (w == 8) {
        const int tile = tz >> 24, mb = tz & 15, hg = (tz >> 8) & 7, kb0 = (tz >> 16) & 7;
        const unsigned l1 = (tz >> 4) & 1;
        if (__builtin_expect(!l1, 0)) {
            CSK(1);
            const uint32_t ep = ld_epoch();
            if (one) {
                kgen_side(in, sbase + A1_SM_W0, bars - 24);
                if (tile < 128) { first_x(); issue_x(2, kb0 + 2); expect(); }
                asm volatile("cp.async.bulk.wait_group 0;" ::: "memory");
            }
            __syncwarp();
            asm volatile("bar.arrive 10, 96;" ::: "memory");
            CSK(6);
            if (tile < 128) {
                await_all(96 + 32 * KG_HG * hg, ep * (KG_HG ? 15 : 120));
                if (one) { issue_w(0); issue_w(1); issue_w(2); }
            }
            CSK(7);
            asm volatile("bar.sync 3, 384;" ::: "memory");
            if (tile < 128 && one) {
                fence_async_smem();
                issue_x(3, kb0 + 3); issue_w(3);
                mbar_expect_tx(bars + 240, 20480);
                bulk_load(sbase + A1_SM_W0, in.x + (size_t)(mb * 128 + hg * 16) * DM, 20480, bars + 240);
            }
            __syncwarp();
            CSK(9);
        } else asm volatile("bar.sync 3, 64;" ::: "memory");
        if (tile < 128 && elect()) {
#pragma unroll 1
            for (unsigned kb = A1_NST; kb < 10; kb++) {
                mbar_wait(bars + 8 * (A1_NST + kb % A1_NST), ((kb / A1_NST) - 1) & 1);
                if (l1 && kb < 9) mbar_wait(bar_rd + 8 * (kb - A1_NST), 0);
                mbar_expect_tx(bars + 8 * (kb % A1_NST), A1_STAGE);
                issue_x(kb, kb < 5 ? kb + kb0 : kb - kb0); issue_w(kb);
                if (kb == (l1 ? A1_WOAT : 9)) {
                    if (!l1) { mbar_wait(bar_stat, 0); asm volatile("fence.proxy.async.global;" ::: "memory"); }
                    mbar_expect_tx(bar_wo, 8 * WOB);
                    bulk_load(sbase + A1_SM_W0, wo + hg * 8 * WOB, 2 * WOB, bar_wo);
                }
            }
            mbar_wait(bars + 8 * (A1_NST + 3), 1);
            bulk_load(sbase + A1_SM_W3, wo + (hg * 8 + 3) * WOB, 3 * WOB, bar_wo);
        }
        CSA(4); CSA_END;
        return;
    }
    {
        if (w < 8 && one) {
#pragma unroll 1
            for (uint32_t c = (w & 4 ? w & 2 ? 0x1111112'01111111ull : 0x1111111'01111184ull : w & 2 ? 0x3122222'01111111ull : 0x1111132'02220000ull) >> (32 * (w & 1)), b = bars + 56 * w; c; c >>= 4, b += 8)
                if (c & 15) mbar_init(b, c & 15);
            asm volatile("fence.mbarrier_init.release.cluster;" ::: "memory");
        }
        __syncwarp();
        asm volatile("bar.sync 0, 384;" ::: "memory");
        if (layer) {
            if (w == 9) asm volatile("bar.arrive 3, 64;" ::: "memory");
        } else {
            if (gen) { SPAN(0, 0); SPAN(0, 1); kgen_tables(in, reinterpret_cast<uint4*>(stg + 3 * A1_STAGE), w11, kp); }
            else if (w != 11 && w11 > 1) asm volatile("bar.arrive 9, 352;" ::: "memory");
            __syncwarp();
            if (w11 < 2) {
                asm volatile("bar.sync 10, 96;" ::: "memory");
                kgen_sums(in, sbase + A1_SM_W0, w11);
                __syncwarp();
                asm volatile("bar.arrive 9, 352;" ::: "memory");
                CSK(1);
            }
            if (w == 9) asm volatile("bar.sync 3, 384;" ::: "memory"); else asm volatile("bar.arrive 3, 384;" ::: "memory");
        }
    }
    tz = __shfl_sync(~0u, tv.z + (uint32_t)(pb >> 32), 0);
    const int tile = tz >> 24, mb = tz & 15, hg = (tz >> 8) & 7;
    float2* rst = reinterpret_cast<float2*>(stg + A1_SM_RS) + 8;
    if (wg == 2) {
        if (w == 11 && layer == 0) {
            asm volatile("bar.sync 9, 352;" ::: "memory");
            CSK(5);
            if (one) publish(64);
            __syncwarp();
            CSK(6);
        }
        if (tile >= 128) { sm_idle(layer); return; }
        if (w == 10) {
            if (one) { prefetch_tmap(&tmR); prefetch_tmap(&tmX1); }
            uint32_t ns;
            asm volatile("mov.u32 %0, %nsmid;" : "=r"(ns));
            if (MAP && ns != 132) __trap();
        }
        __syncwarp();
        if (w == 9) {
            if (layer && one) {
                mbar_expect_tx(bar_stat, 3840);
                bulk_load(sbase + A1_SM_XB, g_xb + tile * 240, 3840, bar_stat);
            }
            __syncwarp();
            uint4* pre = of + (mb * 8 + hg) * 1280 + (tid - 288);
#pragma unroll 1
            for (int k = 0; k < 5 + 5 * layer; k++) {
#pragma unroll
                for (int i = 0; i < 8; i++) asm volatile("st.global.v4.u32 [%0], {%1,%1,%1,%1};" ::"l"(pre + 32 * i), "r"(~0u) : "memory");
                pre += k < 5 ? 256 : XCP / 8;
                if (k == 4) {
                    CSA(2);
                    asm volatile("fence.acq_rel.gpu;" ::: "memory");
                    asm volatile("fence.proxy.async.global;" ::: "memory");
                    __syncwarp();
                    if (tid == 288) mbar_arrive(bar_done);
                    CSA(3);
                    pre = reinterpret_cast<uint4*>(g_yT) + tile * (5 * XCP / 8) + (tid - 288);
                }
            }
            if (layer == 0) {
                asm volatile("griddepcontrol.launch_dependents;" ::: "memory");
                await_all(64, ld_epoch() * gridDim.x);
                CSA(5);
                float4 a[2] = {};
#pragma unroll
                for (int k = 0; k < 10; k++)
#pragma unroll
                    for (int h = 0; h < 2; h++) {
                        const int c4 = min(tid - 288 + 32 * h, 59);
                        const float4 v = __ldcg(reinterpret_cast<const float4*>(g_csp + (k / 5) * 9600 + (k % 5) * 640 + hg * 80) + c4 + (c4 / 20) * 780);
                        a[h].x += v.x; a[h].y += v.y; a[h].z += v.z; a[h].w += v.w;
                    }
#pragma unroll
                for (int h = 0; h < 2; h++)
#pragma unroll
                    for (int k = 0; k < 4; k++) {
                        const float c = 0.5f * (k == 0 ? a[h].x : k == 1 ? a[h].y : k == 2 ? a[h].z : a[h].w), c1 = c - rbf(c), c2 = c1 - rbf(c1);
                        *reinterpret_cast<uint4*>(stg + A1_SM_XB + (4 * min(tid - 288 + 32 * h, 59) + k) * 16) = make_uint4(pack2(c, c1), pack2(c2, 0.f), 0u, 0u);
                    }
                fence_async_smem();
                __syncwarp();
                if (one) {
                    bulk_store(g_xb + tile * 240, sbase + A1_SM_XB, 3840);
                    asm volatile("cp.async.bulk.commit_group;" ::: "memory");
                    asm volatile("cp.async.bulk.wait_group.read 0;" ::: "memory");
                    mbar_arrive(bar_stat);
                }
                __syncwarp();
                CSA(1);
            }
            TSTAMP1T(9, 288);
        } else {
            const int j = tid - 320;
            const uint32_t tag = ld_epoch();
            if (tid == 352) sm_started(layer);
            const int ch = j & 7, kg = (j >> 3) & 3;
            const unsigned char* src = stg + (layer ? (j >> 5) * 8192 + (hg & 3) * 2048 : A1_SM_W0 + (j >> 2) * 1280);
            const int of0 = layer ? kg * 128 + ((ch ^ kg) << 4) : (j & 7) << 4, ofx = layer ? 576 : 64, ofy = layer ? 1024 : 128;
            float s[8], q[8], p0[8];
#pragma unroll
            for (int i = 0; i < 8; i++) { s[i] = 0.f; q[i] = 0.f; }
#pragma unroll 1
            for (int it = 0; it < 5; it++) {
                uint4 v[4];
                mbar_wait(layer ? bars + 8 * (it % A1_NST) : bars + 240, layer * it / A1_NST);
#pragma unroll
                for (int k = 0; k < 4; k++) v[k] = *reinterpret_cast<const uint4*>(src + (layer ? (it % A1_NST) * A1_STAGE : it * 256) + (k & 1 ? of0 ^ ofx : of0) + (k >> 1) * ofy);
                if (it == 0) {
                    const uint4 pv = *reinterpret_cast<const uint4*>(src + (layer ? ch << 4 : 0));
                    const uint32_t w[4] = {pv.x, pv.y, pv.z, pv.w};
#pragma unroll
                    for (int i = 0; i < 4; i++) { p0[2 * i] = __uint_as_float((layer ? w[i] : w[0]) << 16); p0[2 * i + 1] = __uint_as_float(layer ? w[i] & 0xffff0000u : w[0] << 16); }
                }
                asm volatile("" :: "r"(v[0].x), "r"(v[1].x), "r"(v[2].x), "r"(v[3].x), "f"(p0[0]) : "memory");
                __syncwarp();
                if ((tid & 31) == 0) mbar_arrive(bar_rd + 8 * it);
#pragma unroll
                for (int k = 0; k < 4; k++) {
                    const uint32_t w[4] = {v[k].x, v[k].y, v[k].z, v[k].w};
#pragma unroll
                    for (int i = 0; i < 4; i++) {
                        const float a = __uint_as_float(w[i] << 16) - p0[2 * i], b = __uint_as_float(w[i] & 0xffff0000u) - p0[2 * i + 1];
                        s[2 * i] += a; s[2 * i + 1] += b; q[2 * i] = fmaf(a, a, q[2 * i]); q[2 * i + 1] = fmaf(b, b, q[2 * i + 1]);
                    }
                }
            }
            float o[4];
            int row;
            if (layer == 0) {
                float s0 = ((s[0] + s[1]) + (s[2] + s[3])) + ((s[4] + s[5]) + (s[6] + s[7])), q0 = ((q[0] + q[1]) + (q[2] + q[3])) + ((q[4] + q[5]) + (q[6] + q[7]));
#pragma unroll
                for (int o = 1; o <= 2; o <<= 1) { s0 += __shfl_xor_sync(~0u, s0, o); q0 += __shfl_xor_sync(~0u, q0, o); }
                if ((j & 3) == 0) {
                    const float d = s0 * (1.0f / DM);
                    const uint32_t ms = pack2(p0[0] + d, sqrt_apx(rbf(rbf(fmaxf(fmaf(-d, d, q0 * (1.0f / DM)), 0.f)) + 1e-5f)));
                    asm volatile("st.global.cg.u64 [%0], %1;" ::"l"(g_rstat + mb * 128 + (j & 4) * 16 + hg * 8 + (j >> 3)), "l"(tagw(ms, tag)) : "memory");
                    g_piv[mb * 128 + hg * 16 + ((j >> 2) & 8) + (j & 4) + ((j >> 3) & 3)] = __ushort_as_bfloat16((unsigned short)ms);
                }
                ulonglong2 v;
#pragma unroll 1
                for (int it = 0; it < SPIN_MAX; it++) {
                    v = ld_tag2(reinterpret_cast<const ulonglong2*>(g_rstat + mb * 128) + j);
                    if (tag_ok(v, tag)) break;
                    __nanosleep(100);
                }
                o[0] = __uint_as_float((uint32_t)v.x << 16); o[1] = rcp_apx(__uint_as_float((uint32_t)v.x & 0xffff0000u));
                o[2] = __uint_as_float((uint32_t)v.y << 16); o[3] = rcp_apx(__uint_as_float((uint32_t)v.y & 0xffff0000u));
                row = 2 * j;
            } else {
#pragma unroll
                for (int i = 0; i < 4; i++) {
                    const bool up = kg & 2;
                    const float ss = __shfl_xor_sync(~0u, up ? s[i] : s[i + 4], 16), qq = __shfl_xor_sync(~0u, up ? q[i] : q[i + 4], 16);
                    s[i] = (up ? s[i + 4] : s[i]) + ss; q[i] = (up ? q[i + 4] : q[i]) + qq; p0[i] = up ? p0[i + 4] : p0[i];
                }
#pragma unroll
                for (int i = 0; i < 2; i++) {
                    const bool up = kg & 1;
                    const float ss = __shfl_xor_sync(~0u, up ? s[i] : s[i + 2], 8), qq = __shfl_xor_sync(~0u, up ? q[i] : q[i + 2], 8);
                    s[i] = (up ? s[i + 2] : s[i]) + ss; q[i] = (up ? q[i + 2] : q[i]) + qq; p0[i] = up ? p0[i + 2] : p0[i];
                }
                uint4* gp = g_halo + 86016 + mb * 512 + j;
                const float d0 = s[0] * (1.0f / 80.0f), d1 = s[1] * (1.0f / 80.0f);
                asm volatile("st.relaxed.gpu.global.v4.f32 [%0], {%1,%2,%3,%4};" ::"l"(gp + hg * 64), "f"(p0[0] + d0), "f"(fmaxf(fmaf(-d0, s[0], q[0]), 0.f)), "f"(p0[1] + d1), "f"(fmaxf(fmaf(-d1, s[1], q[1]), 0.f)) : "memory");
                __nanosleep(ST_SLEEP0);
                uint32_t pw[8][4], todo = 0xff;
#pragma unroll 1
                for (int it = 0; it < SPIN_MAX; it++) {
#pragma unroll
                    for (int k = 0; k < 8; k++)
                        if (todo >> k & 1) asm volatile("ld.relaxed.gpu.global.v4.u32 {%0,%1,%2,%3}, [%4];" : "=r"(pw[k][0]), "=r"(pw[k][1]), "=r"(pw[k][2]), "=r"(pw[k][3]) : "l"(gp + k * 64) : "memory");
#pragma unroll
                    for (int k = 0; k < 8; k++)
                        if (__all_sync(~0u, pw[k][0] != ~0u && pw[k][1] != ~0u && pw[k][2] != ~0u && pw[k][3] != ~0u)) todo &= ~(1u << k);
                    if (!todo) break;
                    __nanosleep(ST_SLEEP);
                }
#pragma unroll
                for (int r = 0; r < 2; r++) {
                    float mean = 0.f, m2 = 0.f;
#pragma unroll
                    for (int k = 0; k < 8; k++) mean += __uint_as_float(pw[k][2 * r]);
                    mean *= 0.125f;
#pragma unroll
                    for (int k = 0; k < 8; k++) {
                        const float dm = __uint_as_float(pw[k][2 * r]) - mean;
                        m2 += fmaf(80.0f * dm, dm, __uint_as_float(pw[k][2 * r + 1]));
                    }
                    o[2 * r] = rbf(mean);
                    o[2 * r + 1] = rcp_apx(rbf(sqrt_apx(rbf(rbf(m2 * (1.0f / DM)) + 1e-5f))));
                }
                row = (j >> 5) * 64 + (j & 7) * 8 + ((j >> 3) & 3) * 2;
                if (hg == 0) *reinterpret_cast<uint32_t*>(g_piv + SEQ + mb * 128 + 2 * (row & 60) + 4 * (row >> 6) + (row & 3)) = __byte_perm(__float_as_uint(o[0]), __float_as_uint(o[2]), 0x7632);
            }
#pragma unroll
            for (int r = 0; r < 2; r++)
                *reinterpret_cast<uint4*>(stg + A1_SM_XA + (row + r) * 16) = make_uint4(__byte_perm(__float_as_uint(-o[2 * r]), 0, 0x3232), __float_as_uint(-o[2 * r]) >> 16, 0u, 0u);
            *reinterpret_cast<float4*>(rst + row + (row >> 6) * 8) = make_float4(o[0], o[1], o[2], o[3]);
            fence_async_smem();
            TSTAMP1T(7, 320); CSA(1);
            if (tid == 320) DBGC(44);
            __syncwarp();
            if ((tid & 31) == 0) mbar_arrive(bar_stat);
        }
        CSA(4); CSA_END;
        if (tid == 320) DBGCAL(0);
        if (tid == WOT) {
            mbar_wait(WO_LATE, 0);
            mbar_wait(bar_done, 0);
            bulk_load(sbase, wo + (hg * 8 + 6) * WOB, 2 * WOB, bar_wo);
            bulk_load(sbase + A1_SM_W0 + 2 * WOB, wo + (hg * 8 + 2) * WOB, WOB, bar_wo);
        }
        __syncwarp();
#define FWA 11
#define FWB 10
        if (w == FWA || w == FWB) {
            const int cw = w == FWB;
            const uint32_t* fl = reinterpret_cast<const uint32_t*>(rsum + 2 * SEQ) + (((layer * 16 + mb) * 2 + cw) * 8 + (tid & 7)) * FSTR;
            const unsigned char* src = reinterpret_cast<const unsigned char*>(of) + mb * 163840 + cw * 10240 + (tid & 7) * 20480;
            const uint32_t sl = sbase + (cw ? A1_SM_A1 : A1_SM_A0);
            mbar_wait(cw ? bar_done : bar_kvf, 0);
            if ((tid & 31) == 0) {
                mbar_expect_tx(bar_f2 + 64 * cw + 64, 10240);
                tma_load_3d(sl + 51200, &tmR, layer ? 0 : hg * 80, layer ? hg * 80 : mb * 64, layer ? mb * 2 + cw : cw, bar_f2 + 64 * cw + 64);
            }
            __syncwarp();
            uint32_t pend = 0xffu & ~(1u << hg), v = 0;
            const uint32_t bo = wo_off((tid & 7) + ((tid & 7) < hg)) >> 4, lt = (1u << (tid & 31)) - 1;
#pragma unroll 1
            for (int it = 0; pend && it < 2 * SPIN_MAX; it++) {
                if (v != 4 && (pend >> (tid & 31) & 1)) asm volatile(A1_FLD " %0, [%1];" : "=r"(v) : "l"(fl) : "memory");
                uint32_t fr;
                asm volatile("{\n.reg .pred p;\nmbarrier.test_wait.parity.shared::cta.b64 p, [%1], 0;\nselp.b32 %0, 1, 0, p;\n}" : "=r"(fr) : "r"(bar_e2 + 16 * cw + (tid & 1) * 8) : "memory");
                fr = __ballot_sync(~0u, fr);
                uint32_t m = __ballot_sync(~0u, v == 4 || it >= A1_FSPIN) & pend;
                const int q = 8 - __popc(pend) + __popc(m & lt);
                m &= __ballot_sync(~0u, q < ((fr & 2) ? 8 : (fr & 1) ? 7 : 5));
                pend ^= m;
                if (m >> (tid & 31) & 1) DBGC(12 + cw * 8 + (tid & 7));
                if (!m) __nanosleep(A1_FSLEEP);
                else asm volatile("fence.proxy.async.global;" ::: "memory");
                if (m >> (tid & 31) & 1) {
                    bulk_load(q == 7 && !cw ? sbase + A1_SM_W0 : sl + (q < 6 ? q : q - 6) * 10240, src, 10240, bar_f2 + 64 * cw + 8 * q);
                    asm volatile("st.shared.u32 [%0], %1;" ::"r"(que + 32 * cw + 4 * q), "r"(bo) : "memory");
                    mbar_expect_tx(bar_f2 + 64 * cw + 8 * q, 10240);
                    DBGC(44 + cw * 8 + q);
                }
                __syncwarp();
            }
        }
    } else if (tile < 128) {
        SPAN(1 + 4 * layer, 0);
        constexpr int on = 1;
        float acc[120];
        const int lane = tid & 31, warp = w & 7, g = lane >> 2, t = lane & 3;
        if (on) {
            SPAN(1 + 4 * layer, 1);
            TSTAMP1(0);
            if (threadIdx.x == 0) { GSTAMP(g_tim1, 15); }
            TSTAMP3(0);
            if (tid == 0) TSTAMP2(0);
            TSTAMP4(0);
            if (tid == 0) DBGC(60);
            if (layer == 0) a1_mainloop<0>(acc, sbase, bars, wg, tile); else a1_mainloop<1>(acc, sbase, bars, wg, tile);
            uint32_t ok;
            asm volatile("{\n.reg .pred p;\nmbarrier.test_wait.parity.shared::cta.b64 p, [%1], 0;\nselp.b32 %0, 1, 0, p;\n}" : "=r"(ok) : "r"(bar_stat) : "memory");
            if (tid == 128 && !ok) mbar_arrive(bars + 160);
            __syncwarp();
            mbar_wait(bar_stat, 0);
            wgmma_fence();
            wgmma_n240<0, 0>(acc, make_desc(sbase + A1_SM_XA + wg * 1024, 0, 128, 0), make_desc(sbase + A1_SM_XB, 0, 128, 0), 1);
            wgmma_commit();
            if (tid == 128 && ok) mbar_arrive(bars + 160);
            mbar_wait(bars + 8 * (A1_NST + 3), 1);
        }
        const float2* rw = rst + 16 * warp + 8 * wg;
        const float rb0 = rw[g + 8].y, ra = rw[g].y * 0.22360679774997896f, rb = rb0 * 0.22360679774997896f;
        wgmma_wait<0>();
        if ((tid & 127) == 0) mbar_arrive(bar_done);
        TSTAMP1(2); CSA(1);
        TSTAMP1T(13, 224);
        if ((tid & 127) == 0) DBGC(62 - wg);
        uint32_t f[2][30];
#pragma unroll
        for (int j = 10; j < 30; j++) f[1][j] = pack2(acc[4 * j + 2], acc[4 * j + 3]);
        if ((warp & 3) == 3) {
            uint4* hout = g_halo + (((layer * 16 + mb) * 8 + hg) * 2 + wg) * 168;
#pragma unroll
            for (int j = 0; j < 20; j += 4)
                asm volatile("st.relaxed.gpu.global.v4.u32 [%0], {%1,%2,%3,%4};" ::"l"(hout + 8 * j + lane), "r"(f[1][10 + j]), "r"(f[1][11 + j]), "r"(f[1][12 + j]), "r"(f[1][13 + j]) : "memory");
            if (t == 0) asm volatile("st.relaxed.gpu.global.f32 [%0], %1;" ::"l"(reinterpret_cast<float*>(hout + 160) + g), "f"(rb0) : "memory");
        }
        TSTAMP1T(12, 224);
        const uint32_t kvw = sbase + A1_SM_KV + (16 * warp + 8 * wg) * A1_KVP;
        const uint32_t mrow = kvw + (lane & 7) * A1_KVP + (lane >> 3) * 16;
#pragma unroll
        for (int j = 0; j < 20; j += 4) stsm_x4(mrow + 16 * A1_KVP + 16 * j, f[1][10 + j], f[1][11 + j], f[1][12 + j], f[1][13 + j]);
        __syncwarp();
        if (lane == 0 && (warp & 3) != 3) mbar_arrive(bar_kv + 8 * (warp + 1));
#pragma unroll
        for (int j = 0; j < 30; j++) f[0][j] = pack2(acc[4 * j], acc[4 * j + 1]);
        stsm_x4(mrow + 8 * A1_KVP + 160, f[0][20], f[0][21], f[0][22], f[0][23]);
        stsm_x4(mrow + 8 * A1_KVP + 224, f[0][24], f[0][25], f[0][26], f[0][27]);
        asm volatile("stmatrix.sync.aligned.m8n8.x2.shared.b16 [%0], {%1,%2};" ::"r"(mrow + 8 * A1_KVP + 288), "r"(f[0][28]), "r"(f[0][29]) : "memory");
#pragma unroll
        for (int j = 0; j < 10; j++) f[1][j] = pack2(acc[4 * j + 2], acc[4 * j + 3]);
        __syncwarp();
        uint32_t vb[10][2], vp[12], kp[12];
#pragma unroll
        for (int j = 0; j < 10; j += 2) ldsm_x4_t(&vb[j][0], kvw + (8 + (lane & 15)) * A1_KVP + 160 + (lane >> 4) * 16 + 16 * j);
        const bool up0 = 2 * t > g, up1 = 2 * t + 1 > g, edge = (mb | (warp & 3)) == 0;
        float rk[4];
        auto above = [&]() {
            mbar_wait(bar_kv + 8 * warp, 0);
#pragma unroll
            for (int j = 0; j < 12; j += 4) ldsm_x4(&kp[j], mrow + 16 * j);
            rk[0] = rw[2 * t - (up0 ? 8 : 0)].y; rk[1] = rw[2 * t + 1 - (up1 ? 8 : 0)].y;
#pragma unroll
            for (int j = 0; j < 12; j += 4) ldsm_x4_t(&vp[j], mrow + 160 + 16 * j - (j == 8 ? (lane & 16) * 2 : 0));
            __syncwarp();
            if (lane == 0) mbar_arrive(bar_kvf);
        };
        auto halo = [&]() {
            if (lane == 0) mbar_arrive(bar_kvf);
            const uint4* hin = g_halo + (((layer * 16 + mb - 1) * 8 + hg) * 2 + wg) * 168;
            uint32_t hv[22] = {};
            rk[0] = rw[2 * t].y; rk[1] = rw[2 * t + 1].y;
            if (mb > 0) {
#pragma unroll 1
                for (int it = 0; it < SPIN_MAX; it++) {
#pragma unroll
                    for (int k = 0; k < 20; k += 4)
                        asm volatile("ld.relaxed.gpu.global.v4.u32 {%0,%1,%2,%3}, [%4];" : "=r"(hv[k]), "=r"(hv[k + 1]), "=r"(hv[k + 2]), "=r"(hv[k + 3]) : "l"(hin + 8 * k + lane) : "memory");
                    asm volatile("ld.relaxed.gpu.global.v2.u32 {%0,%1}, [%2];" : "=r"(hv[20]), "=r"(hv[21]) : "l"(reinterpret_cast<const uint2*>(hin + 160) + t) : "memory");
                    uint32_t m = max(hv[20], hv[21]);
#pragma unroll
                    for (int k = 0; k < 20; k += 2) m = __vimax3_u32(m, hv[k], hv[k + 1]);
                    if (!__any_sync(~0u, m == ~0u)) break;
                }
            }
            if (lane == 0) DBGC(52 - 16 * wg);
#pragma unroll
            for (int j = 0; j < 10; j++) {
                kp[j] = hv[j];
                asm volatile("movmatrix.sync.aligned.m8n8.trans.b16 %0, %1;" : "=r"(vp[j]) : "r"(hv[10 + j]));
            }
            if (up0) rk[0] = __uint_as_float(hv[20]);
            if (up1) rk[1] = __uint_as_float(hv[21]);
        };
        rk[2] = rw[2 * t + (up0 ? 0 : 8)].y; rk[3] = rw[2 * t + 1 + (up1 ? 0 : 8)].y;
        uint32_t qs[4][2];
#pragma unroll
        for (int h = 0; h < 4; h++) {
            qs[h][0] = (t >> 1) == (h & 1) ? f[0][5 * (h >> 1) + 2] : 0u; qs[h][1] = (t >> 1) == (h & 1) ? f[1][5 * (h >> 1) + 2] : 0u;
            asm volatile("" : "+r"(qs[h][0]), "+r"(qs[h][1]));
        }
#pragma unroll
        for (int j = 0; j < 10; j++) asm volatile("" : "+r"(f[0][j]), "+r"(f[1][j]), "+r"(f[0][10 + j]));
        if (warp & 3) above(); else if (wg) halo();
        TSTAMP1T(10, 64); CSA(2);
        if (warp && !wg) mbar_wait(bars + 416 + 8 * warp, 0);
        CSA(3);
        float sc[4][3][4];
#pragma unroll
        for (int h = 0; h < 4; h++) {
            const int jb = 5 * (h >> 1) + 3 * (h & 1), js = 5 * (h >> 1) + 2;
#pragma unroll
            for (int nt = 1; nt < 3; nt++) {
#pragma unroll
                for (int e = 0; e < 4; e++) sc[h][nt][e] = 0.f;
                mma_bf16(sc[h][nt], f[0][jb], f[1][jb], f[0][jb + 1], f[1][jb + 1], f[nt - 1][10 + jb], f[nt - 1][11 + jb]);
                mma_bf16_k8(sc[h][nt], qs[h][0], qs[h][1], f[nt - 1][10 + js]);
            }
        }
        if (warp == 0) halo();
        TSTAMP1(8); CSA(4);
#pragma unroll
        for (int h = 0; h < 4; h++) {
            const int jb = 5 * (h >> 1) + 3 * (h & 1), js = 5 * (h >> 1) + 2;
#pragma unroll
            for (int e = 0; e < 4; e++) sc[h][0][e] = 0.f;
            mma_bf16(sc[h][0], f[0][jb], f[1][jb], f[0][jb + 1], f[1][jb + 1], kp[jb], kp[jb + 1]);
            mma_bf16_k8(sc[h][0], qs[h][0], qs[h][1], kp[js]);
        }
        TSTAMP1T(3, 64);
        float p[4][4], sum[4][2];
        uint32_t lg[4][2], mx[4];
        const float rl[4] = {rk[0] * ra, rk[1] * ra, rk[2] * rb, rk[3] * rb};
        auto max2 = [](uint32_t a, uint32_t b) { uint32_t r; asm("max.bf16x2 %0, %1, %2;" : "=r"(r) : "r"(a), "r"(b)); return r; };
#pragma unroll
        for (int h = 0; h < 4; h++) {
            lg[h][0] = pack2((up0 ? sc[h][0][0] : sc[h][1][0]) * rl[0], (up0 ? sc[h][1][2] : sc[h][2][2]) * rl[2]);
            lg[h][1] = pack2((up1 ? sc[h][0][1] : sc[h][1][1]) * rl[1], (up1 ? sc[h][1][3] : sc[h][2][3]) * rl[3]);
            if (edge) {
                if (up0) lg[h][0] = __byte_perm(lg[h][0], 0xce6eu, 0x3254);
                if (up1) lg[h][1] = __byte_perm(lg[h][1], 0xce6eu, 0x3254);
            }
            mx[h] = max2(lg[h][0], lg[h][1]);
        }
#pragma unroll
        for (int o = 1; o <= 2; o <<= 1)
#pragma unroll
            for (int h = 0; h < 4; h++) mx[h] = max2(mx[h], __shfl_xor_sync(~0u, mx[h], o));
#pragma unroll
        for (int h = 0; h < 4; h++)
#pragma unroll
            for (int r = 0; r < 2; r++) {
                const float m = __uint_as_float(r ? mx[h] & 0xffff0000u : mx[h] << 16);
#pragma unroll
                for (int e = 0; e < 2; e++)
                    asm("ex2.approx.ftz.f32 %0, %1;" : "=f"(p[h][2 * r + e]) : "f"((__uint_as_float(r ? lg[h][e] & 0xffff0000u : lg[h][e] << 16) - m) * 1.4426950408889634f));
                sum[h][r] = p[h][2 * r] + p[h][2 * r + 1];
            }
#pragma unroll
        for (int o = 1; o <= 2; o <<= 1)
#pragma unroll
            for (int h = 0; h < 4; h++)
#pragma unroll
                for (int r = 0; r < 2; r++) sum[h][r] += __shfl_xor_sync(~0u, sum[h][r], o);
        TSTAMP1T(5, 64); CSA(5);
        const uint32_t mu = (up0 ? 0xffffu : 0u) | (up1 ? 0xffff0000u : 0u);
        uint32_t ob[10][2];
#pragma unroll
        for (int P = 0; P < 2; P++) {
            float os[2][4];
#pragma unroll
            for (int e = 0; e < 2; e++) {
                const int h = 2 * P + e;
                const float i0 = rcp_apx(sum[h][0]), i1 = rcp_apx(sum[h][1]);
                const uint32_t w0 = pack2(p[h][0] * rk[0] * i0, p[h][1] * rk[1] * i0), w1 = pack2(p[h][2] * rk[2] * i1, p[h][3] * rk[3] * i1);
#pragma unroll
                for (int dt = 0; dt < 3; dt++) {
                    const int j = 5 * P + (dt < 2 ? 3 * e + dt : 2);
                    float o[4] = {0.f, 0.f, 0.f, 0.f};
                    mma_bf16(o, w0 & ~mu, w1 & mu, 0u, w1 & ~mu, vb[j][0], vb[j][1]);
                    mma_bf16_k8(o, w0 & mu, 0u, vp[j]);
                    if (dt < 2) { ob[j][0] = pack2(o[0], o[1]); ob[j][1] = pack2(o[2], o[3]); }
                    else { os[e][0] = o[0]; os[e][1] = o[1]; os[e][2] = o[2]; os[e][3] = o[3]; }
                }
            }
#pragma unroll
            for (int k = 0; k < 4; k++) os[0][k] = t < 2 ? os[0][k] : os[1][k];
            ob[5 * P + 2][0] = pack2(os[0][0], os[0][1]); ob[5 * P + 2][1] = pack2(os[0][2], os[0][3]);
        }
        const uint32_t sl = sbase + (wg ? A1_SM_A1 : A1_SM_A0);
        const uint32_t o0 = (warp & 3) * 2048 + g * 64 + ((t ^ (g >> 1)) << 4), o1 = 8192 + (warp & 3) * 512 + g * 32 + ((t ^ ((g >> 2) << 1)) << 3);
        CSA(15);
        mbar_wait(bar_done, 0);
        if (wg == 0) mbar_wait(bar_kvf, 0);
#pragma unroll
        for (int h = 0; h < 2; h++) {
            asm volatile("st.shared.v4.u32 [%0], {%1,%2,%3,%4};" ::"r"(sl + o0 + h * 1024), "r"(ob[0][h]), "r"(ob[1][h]), "r"(ob[2][h]), "r"(ob[3][h]) : "memory");
            asm volatile("st.shared.v4.u32 [%0], {%1,%2,%3,%4};" ::"r"(sl + o0 + h * 1024 + 512), "r"(ob[4][h]), "r"(ob[5][h]), "r"(ob[6][h]), "r"(ob[7][h]) : "memory");
            asm volatile("st.shared.v2.u32 [%0], {%1,%2};" ::"r"(sl + o1 + h * 256), "r"(ob[8][h]), "r"(ob[9][h]) : "memory");
        }
        if (wg && lane == 0) mbar_arrive(bars + 384 + 8 * warp);
        fence_async_smem();
        __syncwarp();
        TSTAMP1T(4, 64); CSA(6);
        TSTAMP1(1);
        TSTAMP2(1);
        const unsigned char* ot = reinterpret_cast<const unsigned char*>(of) + mb * 163840 + wg * 10240;
        if (lane == 0) {
            asm volatile("cp.async.bulk.global.shared::cta.bulk_group [%0], [%1], 2048;" ::"l"(ot + hg * 20480 + (warp & 3) * 2048), "r"(sl + (warp & 3) * 2048) : "memory");
            asm volatile("cp.async.bulk.global.shared::cta.bulk_group [%0], [%1], 512;" ::"l"(ot + hg * 20480 + 8192 + (warp & 3) * 512), "r"(sl + 8192 + (warp & 3) * 512) : "memory");
            asm volatile("cp.async.bulk.commit_group;" ::: "memory");
            if (wg == 0) mbar_arrive(bar_pv);
            asm volatile("cp.async.bulk.wait_group 0;" ::: "memory");
            asm volatile(A1_FRED " [%0], 1;" ::"l"(reinterpret_cast<uint32_t*>(rsum + 2 * SEQ) + (((layer * 16 + mb) * 2 + wg) * 8 + hg) * FSTR) : "memory");
            DBGC(4 + warp);
        }
        TSTAMP4(11); CSA(7);
        float ac2[40];
        const uint64_t db0 = make_desc(sbase, 1024, 256, 3), db1 = make_desc(sbase + 10240, 512, 256, 3), da0 = make_desc(sl, 16, 1024, 2), da1 = make_desc(sl + 8192, 16, 256, 3);
        const uint32_t o7 = wg ? 640 : (A1_SM_W0 - A1_SM_A0) >> 4;
        const uint32_t trow = ((lane & 7) + 8 * (lane >> 4)) * 128 + (((2 * (warp & 3) + ((lane >> 3) & 1)) ^ (lane & 7)) << 4);
        uint32_t xr[10][2];
        mbar_wait(bar_f2 + 64 * wg + 64, 0);
        if (layer == 0) {
#pragma unroll
            for (int j = 0; j < 10; j += 2) ldsm_x4(&xr[j][0], sl + 51200 + (16 * (warp & 3) + (lane & 15)) * 160 + (lane >> 4) * 16 + 16 * j);
        } else {
#pragma unroll
            for (int j = 0; j < 10; j += 2) ldsm_x4_t(&xr[j][0], sl + 51200 + trow + 1024 * j);
        }
        const uint32_t ri = __shfl_sync(~0u, layer * SEQ + (wg * 2 + ((g >> 1) & 1)) * 512 + (mb * 16 + 4 * (warp & 3) + (g >> 2)) * 2 + (g & 1), lane);
        mbar_wait(bar_wo, 0);
        if (wg) mbar_wait(bar_pv, 0);
        if (wg) asm volatile("bar.sync 2, 128;" ::: "memory"); else asm volatile("bar.sync 1, 128;" ::: "memory");
        TSTAMP2(2); CSA(8);
#pragma unroll
        for (int q = 0; q < 8; q++) {
            uint32_t bo = wo_off(0) >> 4;
            if (q) {
                mbar_wait(bar_f2 + 64 * wg + 8 * q, 0);
                asm volatile("ld.shared.u32 %0, [%1];" : "=r"(bo) : "r"(que + 32 * wg + 4 * q) : "memory");
                bo = __shfl_sync(~0u, bo, 0);
                TSTAMP4(q);
                if (q % 3 == 1) CSA(9 + q / 3);
                if (q == 1 && (tid & 127) == 0) DBGC(29 + 8 * wg);
            }
            wgmma_fence();
#pragma unroll
            for (int j = 0; j < 5; j++) wgmma_n80(ac2, (j < 4 ? da0 : da1) + (q == 7 ? o7 : 0u) + (uint64_t)((q < 6 ? q * 640 : 0) + (j & 2) * 16 + (j & 1) * 2), (j < 4 ? db0 : db1) + bo + (uint64_t)((j & 2) * 160 + (j & 1) * 32), j || q);
            wgmma_commit();
            if (q == 0) {
                wgmma_wait<0>();
                if ((tid & 127) == 0) { mbar_arrive(bar_e2 + 16 * wg); mbar_arrive(bar_e2 + 8); }
            }
            if (q == 2 && wg) {
                wgmma_wait<1>();
                if (tid == 128) mbar_arrive(bar_e2 + 24);
            }
        }
        if ((tid & 127) == 0) DBGC(28 + wg * 8 + 7);
        TSTAMP2(3);
        wgmma_wait<0>();
        TSTAMP2(4); CSA(12);
        if (__any_sync(~0u, ac2[0] != ac2[0] || ac2[2] != ac2[2])) {
#pragma unroll
            for (int i = 0; i < 40; i++) ac2[i] = 0.f;
            uint32_t a[20], an[20];
            auto lda = [&](uint32_t (&r)[20], int h) {
#pragma unroll
                for (int u = 0; u < 4; u++)
                    asm volatile("ld.relaxed.gpu.global.v4.u32 {%0,%1,%2,%3}, [%4];" : "=r"(r[4 * u]), "=r"(r[4 * u + 1]), "=r"(r[4 * u + 2]), "=r"(r[4 * u + 3]) : "l"(ot + h * 20480 + o0 + u * 512) : "memory");
#pragma unroll
                for (int u = 0; u < 2; u++)
                    asm volatile("ld.relaxed.gpu.global.v2.u32 {%0,%1}, [%2];" : "=r"(r[16 + 2 * u]), "=r"(r[17 + 2 * u]) : "l"(ot + h * 20480 + o1 + u * 256) : "memory");
            };
            lda(an, 0);
#pragma unroll 5
            for (int k = lane; k < WOB / 16; k += 32)
                reinterpret_cast<uint4*>(stg + (sl - sbase))[k] = __ldcg(reinterpret_cast<const uint4*>(wo + hg * 8 * WOB) + k);
            __syncwarp();
#pragma unroll 1
            for (int h = 0; h < 8; h++) {
#pragma unroll 1
                for (int it = 0; it < SPIN_MAX; it++) {
                    uint32_t m = 0;
#pragma unroll
                    for (int k = 0; k < 20; k += 2) m = __vimax3_u32(m, an[k], an[k + 1]);
                    if (!__any_sync(~0u, m == ~0u)) break;
                    lda(an, h);
                }
#pragma unroll
                for (int k = 0; k < 20; k++) a[k] = an[k];
                lda(an, min(h + 1, 7));
                const uint32_t bp = h == hg ? sl : sbase + wo_off(h + (h < hg));
                const int r0 = 8 * ((lane & 7) >> 1) + 2 * (lane >> 3) + (lane & 1), r2 = 4 * ((lane & 7) >> 1) + 2 * ((lane >> 3) & 1) + (lane & 1);
#pragma unroll
                for (int n = 0; n < 10; n++) {
                    uint32_t b[12];
                    ldsm_x4_t(b, bp + (n >> 1) * 1024 + r0 * 32 + (((n ^ (r0 >> 2)) & 1) << 4));
                    ldsm_x4_t(b + 4, bp + 5120 + (n >> 1) * 1024 + r0 * 32 + (((n ^ (r0 >> 2)) & 1) << 4));
                    ldsm_x4_t(b + 8, bp + 10240 + (n >> 1) * 512 + r2 * 32 + (((n ^ (r2 >> 2)) & 1) << 4));
                    mma_bf16(ac2 + 4 * n, a[0], a[8], a[1], a[9], b[0], b[1]); mma_bf16(ac2 + 4 * n, a[2], a[10], a[3], a[11], b[2], b[3]);
                    mma_bf16(ac2 + 4 * n, a[4], a[12], a[5], a[13], b[4], b[5]); mma_bf16(ac2 + 4 * n, a[6], a[14], a[7], a[15], b[6], b[7]);
                    mma_bf16(ac2 + 4 * n, a[16], a[18], a[17], a[19], b[8], b[9]);
                }
            }
        }
#pragma unroll
        for (int j = 0; j < 10; j++)
#pragma unroll
            for (int hh = 0; hh < 2; hh++) {
                const uint32_t a = pack2(ac2[4 * j + 2 * hh], ac2[4 * j + 2 * hh + 1]);
                const __nv_bfloat162 r = __hadd2_rn(*reinterpret_cast<const __nv_bfloat162*>(&xr[j][hh]), *reinterpret_cast<const __nv_bfloat162*>(&a));
                xr[j][hh] = *reinterpret_cast<const uint32_t*>(&r);
            }
        const uint32_t so = sl + 30720;
#pragma unroll
        for (int j = 0; j < 10; j += 2) stsm_x4_t(so + trow + 1024 * j, xr[j][0], xr[j][1], xr[j + 1][0], xr[j + 1][1]);
        if (wg) asm volatile("bar.sync 2, 128;" ::: "memory"); else asm volatile("bar.sync 1, 128;" ::: "memory");
        TSTAMP2(5); CSA(13);
        if ((tid & 127) == 0) {
            fence_async_smem();
            asm volatile("cp.async.bulk.tensor.2d.global.shared::cta.bulk_group [%0, {%1, %2}], [%3];" ::"l"(&tmX1), "r"(mb * 128 + 64 * wg), "r"(hg * 80), "r"(so) : "memory");
            asm volatile("cp.async.bulk.commit_group;" ::: "memory");
        }
        __syncwarp();
        const float p0 = *(volatile const float*)&rw[g].x, p1 = *(volatile const float*)&rw[g + 8].x;
        float s[3][4] = {};
        const uint32_t pp[2] = {__byte_perm(__float_as_uint(p0), 0, 0x3232), __byte_perm(__float_as_uint(p1), 0, 0x3232)};
#pragma unroll
        for (int j = 0; j < 10; j += 2) {
            const uint32_t d0 = sub2(xr[j][0], pp[0]), d1 = sub2(xr[j][1], pp[1]), d2 = sub2(xr[j + 1][0], pp[0]), d3 = sub2(xr[j + 1][1], pp[1]);
            mma_bf16(s[0], xr[j][0], xr[j][1], xr[j + 1][0], xr[j + 1][1], 0x3f803f80u, 0x3f803f80u);
            mma_bf16(s[1], d0, d1, d2, d3, d0, d2);
            mma_bf16(s[2], d0, d1, d2, d3, d1, d3);
        }
        if (t == (g >> 1)) {
            float2* rp = rsum + ri;
            asm volatile("red.relaxed.gpu.global.add.v2.f32 [%0], {%1, %2};" ::"l"(rp), "f"(fmaf(-80.f, p0, s[0][0])), "f"((g & 1) ? s[1][1] : s[1][0]) : "memory");
            asm volatile("red.relaxed.gpu.global.add.v2.f32 [%0], {%1, %2};" ::"l"(rp + 4), "f"(fmaf(-80.f, p1, s[0][2])), "f"((g & 1) ? s[2][3] : s[2][2]) : "memory");
        }
        asm volatile("cp.async.bulk.wait_group.read 0;" ::: "memory");
        TSTAMP2(6); CSA(14); CSA_END;
        if (tid == 0) DBGC(63);
        if (tid == 128) DBGC(28);
        if (tid == 0) DBGCAL(2);
        GSTAMP(g_tim1, 14);
        SPAN(1 + 4 * layer, 3);
    }
#undef layer
}

static int h_nsm;
static void* h_sym[11];
static TileTab h_tab[2];
static CUtensorMap h_tmX0, h_tmX1, h_tmR0, h_tmR1, h_tmX1st, h_tmOut;
static KgMaps h_tmW;
typedef CUresult (*PFN_encodeTiled)(CUtensorMap*, CUtensorMapDataType, cuuint32_t, void*, const cuuint64_t*, const cuuint64_t*,
                                    const cuuint32_t*, const cuuint32_t*, CUtensorMapInterleave, CUtensorMapSwizzle,
                                    CUtensorMapL2promotion, CUtensorMapFloatOOBfill);
static void make_tmap(CUtensorMap* tm, const void* ptr, uint64_t cols, uint64_t rows, uint32_t bc, uint32_t br, CUtensorMapSwizzle sw, uint64_t pitch = 0, uint64_t hi = 0, uint32_t bh = 2) {
    static PFN_encodeTiled fn = nullptr;
    if (!fn) {
        void* p = nullptr; cudaDriverEntryPointQueryResult qr;
        cudaGetDriverEntryPoint("cuTensorMapEncodeTiled", &p, cudaEnableDefault, &qr);
        fn = (PFN_encodeTiled)p;
    }
    if (br == 0) {
        cuuint64_t dims[5] = {16, 2, rows / 8, 4, cols / 16}; cuuint64_t strides[4] = {cols * 2, cols * 16, cols * 4, 32};
        cuuint32_t box[5] = {16, 2, bc, 4, 5}; cuuint32_t es[5] = {1, 1, 1, 1, 1};
        fn(tm, CU_TENSOR_MAP_DATA_TYPE_BFLOAT16, 5, const_cast<void*>(ptr), dims, strides, box, es, CU_TENSOR_MAP_INTERLEAVE_NONE, sw,
           CU_TENSOR_MAP_L2_PROMOTION_L2_128B, CU_TENSOR_MAP_FLOAT_OOB_FILL_NONE);
        return;
    }
    if (hi == 16) {
        cuuint64_t dims[4] = {16, 32, 120, 20}; cuuint64_t strides[3] = {3840, 32, 32 * 3840};
        cuuint32_t box[4] = {16, 32, 5, 2}; cuuint32_t es[4] = {1, 1, 1, 1};
        fn(tm, CU_TENSOR_MAP_DATA_TYPE_BFLOAT16, 4, const_cast<void*>(ptr), dims, strides, box, es, CU_TENSOR_MAP_INTERLEAVE_NONE, sw,
           CU_TENSOR_MAP_L2_PROMOTION_L2_128B, CU_TENSOR_MAP_FLOAT_OOB_FILL_NONE);
        return;
    }
    if (bh == 0) {
        cuuint64_t dims[5] = {64, 64, 2, 16, 10}; cuuint64_t strides[4] = {pitch * 2, hi * 2, cols * 2, rows * 2};
        cuuint32_t box[5] = {64, 64, 2, 1, 1}; cuuint32_t es[5] = {1, 1, 1, 1, 1};
        fn(tm, CU_TENSOR_MAP_DATA_TYPE_BFLOAT16, 5, const_cast<void*>(ptr), dims, strides, box, es, CU_TENSOR_MAP_INTERLEAVE_NONE, sw,
           CU_TENSOR_MAP_L2_PROMOTION_L2_128B, CU_TENSOR_MAP_FLOAT_OOB_FILL_NONE);
        return;
    }
    if (hi) {
        cuuint64_t dims[3] = {cols, rows, hi == 64 ? 32u : 2u}; cuuint64_t strides[2] = {pitch * 2, hi * 2};
        cuuint32_t box[3] = {bc, br, bh}; cuuint32_t es[3] = {1, 1, 1};
        fn(tm, CU_TENSOR_MAP_DATA_TYPE_BFLOAT16, 3, const_cast<void*>(ptr), dims, strides, box, es, CU_TENSOR_MAP_INTERLEAVE_NONE, sw,
           CU_TENSOR_MAP_L2_PROMOTION_L2_128B, CU_TENSOR_MAP_FLOAT_OOB_FILL_NONE);
        return;
    }
    cuuint64_t dims[2] = {cols, rows}; cuuint64_t strides[1] = {(pitch ? pitch : cols) * 2};
    cuuint32_t box[2] = {bc, br}; cuuint32_t es[2] = {1, 1};
    fn(tm, CU_TENSOR_MAP_DATA_TYPE_BFLOAT16, 2, const_cast<void*>(ptr), dims, strides, box, es, CU_TENSOR_MAP_INTERLEAVE_NONE, sw,
       CU_TENSOR_MAP_L2_PROMOTION_L2_128B, CU_TENSOR_MAP_FLOAT_OOB_FILL_NONE);
}
template <typename... Args>
static void launch_pdl(void (*kern)(Args...), int grid, int block, int smem, Args... args) {
    cudaLaunchConfig_t cfg = {};
    cfg.gridDim = dim3(grid); cfg.blockDim = dim3(block); cfg.dynamicSmemBytes = smem; cfg.stream = cudaStreamPerThread;
    cudaLaunchAttribute at[1];
    at[0].id = cudaLaunchAttributeProgrammaticStreamSerialization; at[0].val.programmaticStreamSerializationAllowed = 1;
    cfg.attrs = at; cfg.numAttrs = 1;
    cudaLaunchKernelEx(&cfg, kern, args...);
}
static void launch_stage(int k, void* const* d_in, void* d_out) {
    const Par par = {k > 1 ? nullptr : (const bf16*)d_in[4], (const bf16*)d_in[5], (const bf16*)d_in[6], (const bf16*)d_in[7], (const bf16*)d_in[8], (const bf16*)d_in[9], k > 1, 0, (const bf16*)d_in[0],
                     (uint4*)h_sym[4], (uint4*)h_sym[2], (uint4*)h_sym[6], (uint4*)h_sym[3], (uint4*)h_sym[0], (float*)h_sym[5], (uint4*)h_sym[1], (const bf16*)d_in[1], (const bf16*)d_in[2]};
    auto a1 = h_nsm == 132 ? a1_kernel<true> : a1_kernel<false>;
    switch (k) {
        case 1: a1<<<h_nsm, A1_THREADS, A1_SMEM, cudaStreamPerThread>>>(par, h_tmX0, h_tmR0, h_tmX1st, h_tmW, h_tab[0]); break;
        case 3: launch_pdl(conv_kernel, DM / CV_CPB, CV_THREADS, CV_SMEM, 0, (const uint4*)h_sym[7], (const float4*)h_sym[4], (const bf16*)h_sym[8], (bf16*)h_sym[9], (const uint4*)h_sym[0], h_tmOut); break;
        case 5: launch_pdl(a1, h_nsm, A1_THREADS, A1_SMEM, par, h_tmX1, h_tmR1, h_tmX1st, h_tmW, h_tab[1]); break;
        case 7: launch_pdl(conv_kernel, DM / CV_CPB, CV_THREADS, CV_SMEM, 1, (const uint4*)h_sym[7] + SEQ / 8, (const float4*)h_sym[4] + SEQ / 2, (const bf16*)h_sym[8], (bf16*)h_sym[10], (const uint4*)h_sym[0], h_tmOut); break;
        default: break;
    }
}
static int n_stage_kernels() { return 9; }
static const char* stage_name(int k) { const char* n[] = {"kgen", "a1", "a2", "conv", "tr", "a1", "a2", "conv", "tr"}; return n[k]; }

extern "C" void kernel_launch(void* const* d_in, const int* in_sizes, int n_in, void* d_out, int out_size) {
    (void)in_sizes; (void)n_in; (void)out_size;
    static const void *p_in = nullptr, *p_w1 = nullptr, *p_w2 = nullptr, *p_out = nullptr;
    if (p_in != d_in[0] || p_w1 != d_in[1] || p_w2 != d_in[2] || p_out != d_out) {
        cudaFuncSetAttribute(conv_kernel, cudaFuncAttributeMaxDynamicSharedMemorySize, CV_SMEM);
        cudaFuncSetAttribute(a1_kernel<true>, cudaFuncAttributeMaxDynamicSharedMemorySize, A1_SMEM);
        cudaFuncSetAttribute(a1_kernel<false>, cudaFuncAttributeMaxDynamicSharedMemorySize, A1_SMEM);
        int dev; cudaGetDevice(&dev); cudaDeviceGetAttribute(&h_nsm, cudaDevAttrMultiProcessorCount, dev);
        if (h_nsm != 132) h_nsm = 128;
        cudaGetSymbolAddress(&h_sym[0], g_tap); cudaGetSymbolAddress(&h_sym[1], g_wq); cudaGetSymbolAddress(&h_sym[2], g_wo);
        cudaGetSymbolAddress(&h_sym[3], g_halo); cudaGetSymbolAddress(&h_sym[4], g_sum); cudaGetSymbolAddress(&h_sym[5], g_csp); cudaGetSymbolAddress(&h_sym[6], g_of);
        cudaGetSymbolAddress(&h_sym[7], g_piv); cudaGetSymbolAddress(&h_sym[8], g_x1T); cudaGetSymbolAddress(&h_sym[9], g_xcT); cudaGetSymbolAddress(&h_sym[10], g_yT);
        for (int i = 0; i < 264; i++) {
            const int s = i % 132, h = (s - 64) >> 1;
            const int t = h_nsm != 132 ? s : s < 64 ? ((s >> 1) & 7) * 16 + (s >> 4) * 2 + (s & 1) : s < 120 ? (1 + h % 7) * 16 + 8 + (h / 7) * 2 + (s & 1) : s < 124 ? 128 : s - 116;
            const int hg = (4 * (t >> 6) + (t & 3)) & 7;
            const uint64_t wp = (uint64_t)h_sym[1] + hg * 10 * WQ_STAGE;
            h_tab[i / 132].e[s] = make_uint4((uint32_t)wp, (uint32_t)(wp >> 32), ((t >> 2) & 15) | (i / 132) << 4 | hg << 8 | 5 * (hg >> 2) << 16 | (uint32_t)t << 24, 0);
        }
        void *px1, *px2;
        cudaGetSymbolAddress(&px1, g_x1T); cudaGetSymbolAddress(&px2, g_xcT);
        make_tmap(&h_tmX0, d_in[0], 128 * 640, 64, 64, 64, CU_TENSOR_MAP_SWIZZLE_128B, 1280, 640, 0);
        make_tmap(&h_tmX1, px2, 128, 64 * XCP, 64, 64, CU_TENSOR_MAP_SWIZZLE_128B, XCP, 64, 0);
        make_tmap(&h_tmR0, d_in[0], 640, 1024, 80, 64, CU_TENSOR_MAP_SWIZZLE_NONE, 1280, 640, 1);
        make_tmap(&h_tmR1, px2, 64, 640, 64, 80, CU_TENSOR_MAP_SWIZZLE_128B, XCP, 64, 1);
        make_tmap(&h_tmX1st, px1, 2048, 640, 64, 80, CU_TENSOR_MAP_SWIZZLE_128B, XCP);
        make_tmap(&h_tmW.q, d_in[1], 16, 640, 16, 32, CU_TENSOR_MAP_SWIZZLE_32B, 1920, 16, 5);
        make_tmap(&h_tmW.o, d_in[2], 640, 640, 4, 0, CU_TENSOR_MAP_SWIZZLE_32B);
        make_tmap(&h_tmW.t, d_in[2], 640, 640, 2, 0, CU_TENSOR_MAP_SWIZZLE_32B);
        make_tmap(&h_tmOut, d_out, 640, 1024, 80, 8, CU_TENSOR_MAP_SWIZZLE_NONE, 1280, 640, 1);
        p_in = d_in[0]; p_w1 = d_in[1]; p_w2 = d_in[2]; p_out = d_out;
    }
    for (int k = 0; k < n_stage_kernels(); k++) launch_stage(k, d_in, d_out);
}
```

```cpp
#include <cuda_runtime.h>
#include <cuda_bf16.h>
#include <cuda_fp16.h>
#include <stdint.h>
#include <cuda.h>

typedef __nv_bfloat16 bf16;

constexpr int SEQ = 2048;
constexpr int DM = 640;
constexpr int NMODE = 192;

__device__ __forceinline__ float bf2f(bf16 v) { return __bfloat162float(v); }
__device__ __forceinline__ float rbf(float v) {
    uint32_t r;
    asm("cvt.rn.bf16x2.f32 %0, %1, %2;" : "=r"(r) : "f"(v), "f"(0.f));
    return __uint_as_float(r);
}
__device__ __forceinline__ uint32_t pack2(float lo, float hi) {
    __nv_bfloat162 t = __floats2bfloat162_rn(lo, hi);
    return *reinterpret_cast<uint32_t*>(&t);
}
__device__ __forceinline__ void pdl_sync() {
    asm volatile("griddepcontrol.wait;" ::: "memory");
    asm volatile("griddepcontrol.launch_dependents;" ::: "memory");
}
__device__ __forceinline__ float sqrt_apx(float v) { float r; asm("sqrt.approx.ftz.f32 %0, %1;" : "=f"(r) : "f"(v)); return r; }
__device__ __forceinline__ float rcp_apx(float v) { float r; asm("rcp.approx.ftz.f32 %0, %1;" : "=f"(r) : "f"(v)); return r; }
__device__ __forceinline__ uint32_t smem_u32(const void* p) { return (uint32_t)__cvta_generic_to_shared(p); }

constexpr int TAPB = 2944, TAPE = 928;
__device__ __align__(128) uint4 g_tap[DM * TAPB / 16];
#define XPAD 64
constexpr int XCP = SEQ + XPAD;
__device__ __align__(128) bf16 g_x1T[DM * XCP];
__device__ __align__(128) bf16 g_xcT[DM * XCP];
__device__ __align__(128) uint4 g_of[128 * 1280];
constexpr int WQ_STAGE = 240 * 128, WOB = 80 * 160;
__device__ __align__(128) uint4 g_wq[8 * 10 * WQ_STAGE / 16];
__device__ __align__(128) uint4 g_wo[64 * WOB / 16];
__device__ __align__(128) uint4 g_xb[128 * 240];
__device__ __align__(16) float g_csp[10 * 1920];
#define FSTR 32
__device__ __align__(128) float2 g_sum[2 * SEQ + 256 * FSTR];
__device__ __align__(16) bf16 g_piv[2 * SEQ];
__device__ __align__(128) bf16 g_yT[DM * XCP];
__device__ uint32_t g_epoch;
__device__ __align__(16) unsigned long long g_rstat[SEQ];
__device__ __align__(128) uint4 g_halo[640 * 148];
__device__ __forceinline__ unsigned long long tagw(uint32_t payload, uint32_t tag) { return ((unsigned long long)tag << 32) | payload; }
__device__ __forceinline__ ulonglong2 ld_tag2(const ulonglong2* p) {
    ulonglong2 v;
    asm volatile("ld.relaxed.gpu.global.v2.u64 {%0, %1}, [%2];" : "=l"(v.x), "=l"(v.y) : "l"(p) : "memory");
    return v;
}
__device__ __forceinline__ bool tag_ok(ulonglong2 v, uint32_t tag) { return (uint32_t)(v.x >> 32) == tag && (uint32_t)(v.y >> 32) == tag; }
__device__ __forceinline__ uint32_t ld_epoch() { uint32_t v; asm volatile("ld.relaxed.gpu.global.u32 %0, [%1];" : "=r"(v) : "l"(&g_epoch) : "memory"); return v + 1; }
constexpr int SPIN_MAX = 1 << 20;
__device__ __align__(128) uint32_t g_started[11 * 32];
__device__ __forceinline__ void sm_started(int slot) { asm volatile("red.relaxed.gpu.global.add.u32 [%0], 1;" ::"l"(g_started + slot) : "memory"); }
__device__ __forceinline__ void publish(int slot) {
    asm volatile("fence.proxy.async.global;" ::: "memory");
    asm volatile("red.release.gpu.global.add.u32 [%0], 1;" ::"l"(g_started + slot) : "memory");
}
__device__ __forceinline__ void await_all(int slot, uint32_t want) {
#pragma unroll 1
    for (int it = 0; it < SPIN_MAX; it++) {
        uint32_t v;
        asm volatile("ld.acquire.gpu.global.u32 %0, [%1];" : "=r"(v) : "l"(g_started + slot) : "memory");
        if (__all_sync(~0u, (int)(v - want) >= 0)) break;
        __nanosleep(50);
    }
    asm volatile("fence.proxy.async.global;" ::: "memory");
}
__device__ __noinline__ void sm_idle(int slot) {
    if (threadIdx.x != 288) return;
    asm volatile("fence.acq_rel.gpu;" ::: "memory");
    asm volatile("fence.proxy.async.global;" ::: "memory");
    sm_started(slot);
    const uint32_t want = ld_epoch() * gridDim.x;
    pdl_sync();
#pragma unroll 1
    for (int it = 0; it < SPIN_MAX; it++) {
        uint32_t v;
        asm volatile("ld.relaxed.gpu.global.u32 %0, [%1];" : "=r"(v) : "l"(g_started + slot) : "memory");
        if ((int)(v - want) >= 0) break;
        __nanosleep(100);
    }
}
struct TileTab { uint4 e[132]; };
__device__ __forceinline__ bool elect() {
    uint32_t p;
    asm volatile("{\n.reg .pred p;\nelect.sync _|p, 0xffffffff;\nselp.b32 %0, 1, 0, p;\n}" : "=r"(p));
    return p;
}
#define DBG_SYMS
#define TSTAMP(i)
#define TSTAMP1(i)
#define TSTAMP1T(i, t)
#define TSTAMP1X(i, t)
#define SPAN(k, i)
#define GSTAMP(arr, i)
#define TSTAMP2(i)
#define TSTAMP3(i)
#define TSTAMP4(i)
#define TSTAMPK(i, t)
#define TSTAMPC(i)
#define DBGC(i)
#define DBGV(i, v)
#define DBGCAL(i)

#define CSK(i)
#define CSK_END
#define CSA(i)
#define CSA_END
#define CST(i)
#define CST_END
#define CST_EXTRA 0
__device__ __forceinline__ void mma_bf16(float* d, uint32_t a0, uint32_t a1, uint32_t a2, uint32_t a3, uint32_t b0, uint32_t b1) {
    asm volatile("mma.sync.aligned.m16n8k16.row.col.f32.bf16.bf16.f32 {%0,%1,%2,%3}, {%4,%5,%6,%7}, {%8,%9}, {%0,%1,%2,%3};"
                 : "+f"(d[0]), "+f"(d[1]), "+f"(d[2]), "+f"(d[3]) : "r"(a0), "r"(a1), "r"(a2), "r"(a3), "r"(b0), "r"(b1));
}
__device__ __forceinline__ void mma_bf16_k8(float* d, uint32_t a0, uint32_t a1, uint32_t b0) {
    asm volatile("mma.sync.aligned.m16n8k8.row.col.f32.bf16.bf16.f32 {%0,%1,%2,%3}, {%4,%5}, {%6}, {%0,%1,%2,%3};"
                 : "+f"(d[0]), "+f"(d[1]), "+f"(d[2]), "+f"(d[3]) : "r"(a0), "r"(a1), "r"(b0));
}
__device__ __forceinline__ void ldsm_x4(uint32_t* r, uint32_t addr) {
    asm volatile("ldmatrix.sync.aligned.m8n8.x4.shared.b16 {%0,%1,%2,%3}, [%4];"
                 : "=r"(r[0]), "=r"(r[1]), "=r"(r[2]), "=r"(r[3]) : "r"(addr));
}

__device__ __forceinline__ void ldsm_x4_t(uint32_t* r, uint32_t addr) {
    asm volatile("ldmatrix.sync.aligned.m8n8.x4.trans.shared.b16 {%0,%1,%2,%3}, [%4];"
                 : "=r"(r[0]), "=r"(r[1]), "=r"(r[2]), "=r"(r[3]) : "r"(addr));
}
__device__ __forceinline__ void mbar_init(uint32_t bar, int count) { asm volatile("mbarrier.init.shared::cta.b64 [%0], %1;" ::"r"(bar), "r"(count)); }
__device__ __forceinline__ void mbar_arrive(uint32_t bar) { asm volatile("mbarrier.arrive.shared::cta.b64 _, [%0];" ::"r"(bar) : "memory"); }
__device__ __forceinline__ void mbar_wait(uint32_t bar, uint32_t parity) {
    asm volatile("{\n.reg .pred p;\nWAIT_LOOP:\n"
                 "mbarrier.try_wait.parity.shared::cta.b64 p, [%0], %1;\n"
                 "@p bra.uni WAIT_DONE;\nbra.uni WAIT_LOOP;\nWAIT_DONE:\n}" ::"r"(bar), "r"(parity) : "memory");
}

__device__ __forceinline__ void mbar_expect_tx(uint32_t bar, uint32_t bytes) {
    asm volatile("mbarrier.arrive.expect_tx.shared::cta.b64 _, [%0], %1;" ::"r"(bar), "r"(bytes) : "memory");
}
__device__ __forceinline__ void tma_load_2d(uint32_t dst, const void* tmap, int c0, int c1, uint32_t bar) {
    asm volatile("cp.async.bulk.tensor.2d.shared::cluster.global.mbarrier::complete_tx::bytes [%0], [%1, {%3, %4}], [%2];"
                 ::"r"(dst), "l"(tmap), "r"(bar), "r"(c0), "r"(c1) : "memory");
}
__device__ __forceinline__ void tma_load_3d(uint32_t dst, const void* tmap, int c0, int c1, int c2, uint32_t bar) {
    asm volatile("cp.async.bulk.tensor.3d.shared::cluster.global.mbarrier::complete_tx::bytes [%0], [%1, {%3, %4, %5}], [%2];"
                 ::"r"(dst), "l"(tmap), "r"(bar), "r"(c0), "r"(c1), "r"(c2) : "memory");
}
__device__ __forceinline__ void fence_async_smem() { asm volatile("fence.proxy.async.shared::cta;" ::: "memory"); }
__device__ __forceinline__ void bulk_load(uint32_t dst, const void* src, uint32_t bytes, uint32_t bar) {
    asm volatile("cp.async.bulk.shared::cluster.global.mbarrier::complete_tx::bytes [%0], [%1], %2, [%3];"
                 ::"r"(dst), "l"(src), "r"(bytes), "r"(bar) : "memory");
}
__device__ __forceinline__ void stsm_x4(uint32_t addr, uint32_t r0, uint32_t r1, uint32_t r2, uint32_t r3) {
    asm volatile("stmatrix.sync.aligned.m8n8.x4.shared.b16 [%0], {%1,%2,%3,%4};" ::"r"(addr), "r"(r0), "r"(r1), "r"(r2), "r"(r3) : "memory");
}
__device__ __forceinline__ void stsm_x4_t(uint32_t addr, uint32_t r0, uint32_t r1, uint32_t r2, uint32_t r3) {
    asm volatile("stmatrix.sync.aligned.m8n8.x4.trans.shared.b16 [%0], {%1,%2,%3,%4};" ::"r"(addr), "r"(r0), "r"(r1), "r"(r2), "r"(r3) : "memory");
}
__device__ __forceinline__ void prefetch_tmap(const void* tmap) { asm volatile("prefetch.tensormap [%0];" ::"l"(tmap) : "memory"); }

__device__ __forceinline__ float2 cexp_at(float wr2, float wi, float p) {
    float er;
    asm("ex2.approx.ftz.f32 %0, %1;" : "=f"(er) : "f"(wr2 * p));
    float th = wi * p;
    const float k = rintf(th * 0.15915494309189535f);
    th = fmaf(k, -6.2831854820251465f, th);
    th = fmaf(k, 1.7484555314695172e-7f, th);
    return make_float2(er * __cosf(th), er * __sinf(th));
}
__device__ __forceinline__ float2 cmul(float2 a, float2 b) {
    return make_float2(fmaf(a.x, b.x, -a.y * b.y), fmaf(a.x, b.y, a.y * b.x));
}
__device__ __forceinline__ float2 csqr(float2 a) { return make_float2(fmaf(a.x, a.x, -a.y * a.y), (a.x + a.x) * a.y); }
__device__ __forceinline__ uint32_t packh(float2 v) {
    uint32_t r;
    asm("cvt.rn.f16x2.f32 %0, %1, %2;" : "=r"(r) : "f"(v.y), "f"(v.x));
    return r;
}
__device__ __forceinline__ uint2 packr(float2 v) { return make_uint2(packh(v), packh(make_float2(-v.y, v.x))); }
__device__ __forceinline__ uint32_t hcmul(uint32_t a, uint2 b) {
    const __half2 x = *reinterpret_cast<const __half2*>(&a);
    const __half2 r = __hfma2(__high2half2(x), *reinterpret_cast<const __half2*>(&b.y), __hmul2(__low2half2(x), *reinterpret_cast<const __half2*>(&b.x)));
    return *reinterpret_cast<const uint32_t*>(&r);
}

struct Par { const bf16 *logA, *Aim, *Cre, *Cim, *logdt, *dsk; int layer, pad; const bf16* x; uint4 *sum, *wop, *of, *halo, *tap; float* csp; uint4* wq; const bf16 *wqkv, *wo; };
struct KgMaps { CUtensorMap q, o, t; };

__device__ __forceinline__ void bulk_prefetch(const void* p, uint32_t bytes) { asm volatile("cp.async.bulk.prefetch.L2.global [%0], %1;" ::"l"(p), "r"(bytes) : "memory"); }
__device__ __forceinline__ void bulk_store(void* dst, uint32_t src, uint32_t bytes) { asm volatile("cp.async.bulk.global.shared::cta.bulk_group [%0], [%1], %2;" ::"l"(dst), "r"(src), "r"(bytes) : "memory"); }
__device__ __forceinline__ void kgen_first(const Par& in, const KgMaps& tm, const uint32_t b0, const uint32_t wbar, const bool one) {
    const uint32_t blk = blockIdx.x, sec = (blk >= 40) + (blk >= 80), it = (blk >> 3) - 5 * sec, up = (blk >> 2) & 1, hi = blk >> 6;
    auto fetch = [&](int h) {
        if (blk < 120) asm volatile("cp.async.bulk.tensor.4d.shared::cluster.global.mbarrier::complete_tx::bytes [%0], [%1, {%3, %3, %4, %5}], [%2];"
                                    ::"r"(b0 + 10240 * h), "l"(&tm.q), "r"(wbar + 8 * h), "r"(0), "r"(sec * 40 + (blk & 7) * 5), "r"(2 * it + 10 * (up ^ h)) : "memory");
    };
    auto fetch_o = [&](int i) {
        asm volatile("cp.async.bulk.tensor.5d.shared::cluster.global.mbarrier::complete_tx::bytes [%0], [%1, {%3, %3, %4, %3, %5}], [%2];"
                     ::"r"(b0 + 20480 + i * 5120), "l"(&tm.o + i), "r"(wbar + 16), "r"(0), "r"((blk & 7) * 10 + (hi + i) * 4), "r"(((blk >> 3) & 7) * 5) : "memory");
    };
    if (one) {
#pragma unroll
        for (int i = 0; i < 3; i++) mbar_init(wbar + 8 * i, 1);
        asm volatile("fence.mbarrier_init.release.cluster;" ::: "memory");
        fetch(0);
    }
    __syncwarp();
    if (blk >> 20) __trap();
    if (one) {
        bulk_prefetch(in.wqkv + blk * 9600, 19200);
        fetch(1);
        bulk_prefetch(in.wo + blk * 3200, 6400);
        fetch_o(0);
        if (hi) fetch_o(1);
        mbar_expect_tx(wbar, 10240); mbar_expect_tx(wbar + 8, 10240); mbar_expect_tx(wbar + 16, 5120 + hi * 2560);
        bulk_prefetch(in.x + blk * 10240, 20480);
    }
}
__device__ __forceinline__ void kgen_side(const Par& in, const uint32_t b0, const uint32_t wbar) {
    const uint32_t blk = blockIdx.x, sec = (blk >= 40) + (blk >= 80), it = (blk >> 3) - 5 * sec, cg = (blk >> 3) & 7, hb = blk & 7;
    unsigned char* dst = reinterpret_cast<unsigned char*>(in.wq) + (hb * 10 + it) * WQ_STAGE + sec * 5120;
    if (blk < 120) {
        mbar_wait(wbar, 0);
        CSK(2);
        bulk_store(dst, b0, 5120); bulk_store(dst + 15360, b0 + 5120, 5120);
        mbar_wait(wbar + 8, 0);
        CSK(3);
        bulk_store(dst + 5 * WQ_STAGE, b0 + 10240, 5120); bulk_store(dst + 5 * WQ_STAGE + 15360, b0 + 15360, 5120);
        asm volatile("cp.async.bulk.commit_group;" ::: "memory");
        asm volatile("cp.async.bulk.wait_group 0;" ::: "memory");
        CSK(4);
        publish(96 + 32 * hb);
        CSK(5);
    }
    if (blk < 128) {
        mbar_wait(wbar + 16, 0);
        bulk_store(reinterpret_cast<unsigned char*>(in.wop) + (cg * 8 + (hb == cg ? 0 : hb + (hb < cg))) * WOB + (blk >> 6) * 5120, b0 + 20480, blk < 64 ? 5120 : 7680);
        asm volatile("cp.async.bulk.commit_group;" ::: "memory");
    }
}
__device__ __forceinline__ void kgen_sums(const Par& in, const uint32_t b0, const int h) {
    const int lane = threadIdx.x & 31, blk = blockIdx.x;
    if (blk < 120) {
        float cs[5][4] = {};
#pragma unroll
        for (int a = 0; a < 4; a++)
#pragma unroll
            for (int j = 0; j < 5; j++) {
                uint32_t w[4];
                ldsm_x4_t(w, b0 + h * 10240 + j * 1024 + ((lane >> 4) * 8 + (lane & 7)) * 32 + ((((lane >> 3) ^ (lane >> 2)) & 1) << 4) + (a >> 1) * 5120 + (a & 1) * 512);
                mma_bf16(cs[j], w[0], w[1], w[2], w[3], 0x3f803f80u, 0x3f803f80u);
            }
#pragma unroll
        for (int j = 0; j < 5; j++)
            if ((lane & 3) < 2) in.csp[(blk + 120 * h) * 80 + j * 16 + (lane >> 2) + 8 * (lane & 3)] = (lane & 3) ? cs[j][2] : cs[j][0];
    }
}
struct KgPar { uint32_t pw[4], ph[4], pdt, pdsk; };
__device__ __forceinline__ void kgen_load(const Par& in, const bf16* logA, const int w11, KgPar& k) {
    const uint32_t o = blockIdx.x * 480 + min(w11 * 48, w11 * 32 + 128), ow = o + (threadIdx.x & 31), oh = o + ow + (w11 < 8 ? 64 : 0);
    k.pdt = reinterpret_cast<const unsigned short*>(in.logdt)[ow / 96];
    k.pdsk = reinterpret_cast<const unsigned short*>(in.dsk)[ow / 96];
#pragma unroll
    for (int i = 0; i < 4; i++) {
        const bf16* p = i == 0 ? logA : i == 1 ? in.Aim : i == 2 ? in.Cre : in.Cim;
        k.pw[i] = reinterpret_cast<const uint32_t*>(p)[ow]; k.ph[i] = reinterpret_cast<const unsigned short*>(p)[oh];
    }
}
__device__ __forceinline__ void kgen_tables(const Par& in, uint4* tabs, const int w11, const KgPar& kp) {
    const int lane = threadIdx.x & 31, grp = min(w11 >> 1, 4), warp = w11 - 2 * grp;
    const int blk = blockIdx.x, d = blk * 5 + grp, tid = warp * 32 + lane;
    uint4* tab = tabs + grp * (2 * 256);
    const uint32_t *pw = kp.pw, *ph = kp.ph;
#pragma unroll
    for (int i = 0; i < 3; i++)
        if (i < 2 || w11 * 32 + lane < 36) asm volatile("st.global.v4.u32 [%0], {%1,%1,%1,%1};" ::"l"(in.halo + blk * 740 + w11 * 32 + lane + 352 * i), "r"(~0u));
    __syncwarp();
    if (w11 == 10) {
        if (lane < 16) in.sum[blk * 16 + lane] = make_uint4(0, 0, 0, 0);
        else if (lane < 20) reinterpret_cast<uint32_t*>(in.sum + 2048)[(blk * 4 + lane - 16) * FSTR] = 0;
    } else if (w11 > 1) asm volatile("bar.arrive 9, 352;" ::: "memory");
#pragma unroll
    for (int i = 0; i < 6; i++) tabs[w11 * 256 + 32 * i + lane] = make_uint4(0, 0, 0, 0);
    __syncwarp();
    CSK(1);
    const uint32_t tw = smem_u32(tabs) + w11 * 4096;
    const int g = lane >> 2, t = lane & 3;
    const int mt = lane >> 3, r = lane & 7;
    const uint32_t st1 = tw + mt * 1024 + r * 16, st2 = tw + (mt & 1) * 1024 + (mt >> 1) * 128 + ((r ^ (mt >> 1)) << 4), st3 = tw + 2048 + mt * 128 + ((r ^ mt) << 4);
    const uint32_t lda = tw + (mt & 1) * 1024 + r * 128 + (((mt >> 1) ^ r) << 4), ldb = tw + (mt >> 1) * 1024 + r * 128 + (((mt & 1) ^ r) << 4), ldc = tw + 2048 + r * 128 + ((mt ^ r) << 4);
    auto ldsm = [](uint32_t* v, uint32_t a) {
        asm volatile("ldmatrix.sync.aligned.m8n8.x4.shared.b16 {%0,%1,%2,%3}, [%4];" : "=r"(v[0]), "=r"(v[1]), "=r"(v[2]), "=r"(v[3]) : "r"(a) : "memory");
    };
    auto mma = [](float* c, const uint32_t* a, const uint32_t* b) {
        asm("mma.sync.aligned.m16n8k16.row.col.f32.f16.f16.f32 {%0,%1,%2,%3}, {%4,%5,%6,%7}, {%8,%9}, {%0,%1,%2,%3};"
            : "+f"(c[0]), "+f"(c[1]), "+f"(c[2]), "+f"(c[3]) : "r"(a[0]), "r"(a[1]), "r"(a[2]), "r"(a[3]), "r"(b[0]), "r"(b[1]));
    };
    asm volatile("st.shared.u32 [%0], %1;" ::"r"(tw + 3072), "r"(st1 ^ st2 ^ st3 ^ lda ^ ldb ^ ldc) : "memory");
    if (in.pad) __trap();
    const float dt = rbf(expf(__uint_as_float(kp.pdt << 16)));
    const uint32_t cm = __vmaxu2(__vmaxu2(pw[2] & 0x7fff7fffu, pw[3] & 0x7fff7fffu), __byte_perm(ph[2], ph[3], 0x5410) & 0x7fff7fffu);
    const int ex = min(max((int)(__float_as_uint(__uint_as_float(__reduce_max_sync(~0u, max(cm << 16, cm & 0xffff0000u))) * dt) >> 23), 20), 240);
    const float scale = __uint_as_float((uint32_t)(127 + 10 + 127 - ex) << 23), unscale = 2.0f * __uint_as_float((uint32_t)(ex - 10) << 23);
    float k2048 = 0.f;
    float acc[5][4] = {};
    uint32_t af[4][4] = {};
    auto rest = [&] {
        uint32_t b[4][4], c[8];
#pragma unroll
        for (int k = 0; k < 4; k++) {
            ldsm(b[k], ldb ^ (k << 5));
            if (!(k & 1)) ldsm(c + 2 * k, ldc ^ (k << 5));
        }
#pragma unroll
        for (int k = 0; k < 4; k++) { mma(acc[2], af[k], b[k]); mma(acc[3], af[k], b[k] + 2); mma(acc[4], af[k], c + 2 * k); }
    };
#pragma unroll 1
    for (uint32_t sel = 0x1076; sel < (grp < 4 ? 0x6000u : 0x4000u); sel += 0x2200) {
        rest();
        auto par = [&](int i) { return __uint_as_float(__byte_perm(pw[i], ph[i], sel)); };
        const float wr2 = -rbf(expf(par(0))) * dt * 1.4426950408889634f, wi = par(1) * dt;
        const float2 y1 = cexp_at(wr2, -wi, 1.f), w64 = cexp_at(wr2, wi, 64.f), y4 = csqr(csqr(y1)), z8 = csqr(make_float2(y4.x, -y4.y)), y128 = csqr(make_float2(w64.x, -w64.y));
        float2 h0 = make_float2(1.f, 0.f), g0 = make_float2(par(2) * dt * scale, -par(3) * dt * scale);
        const float2 v2 = csqr(y128), v3 = cmul(v2, y128), v4 = csqr(v2), v8 = csqr(v4), c8 = cmul(g0, v8);
        const uint2 z64 = packr(w64), v[8] = {make_uint2(packh(c8), 0u), packr(y128), packr(v2), packr(v3), packr(v4), packr(cmul(v4, y128)), packr(csqr(v3)), packr(cmul(v4, v3))};
        k2048 += fmaf(c8.x, v8.x, -c8.y * v8.y);
        uint32_t ge[4];
#pragma unroll
        for (int e = 0; e < 8; e++) {
            const uint32_t p = packh(h0), q = packh(g0);
            if (!(e & 1)) ge[e >> 1] = q;
            stsm_x4((st1 ^ (e << 4)) + e * 128, p, e ? hcmul(p, z64) : z64.x, q, hcmul(q, v[1]));
            if (e < 7) { h0 = e ? cmul(h0, z8) : z8; g0 = cmul(g0, y1); }
        }
        __syncwarp();
        uint32_t b[4][4];
#pragma unroll
        for (int k = 0; k < 4; k++) { ldsm(af[k], lda ^ (k << 5)); ldsm(b[k], (ldb ^ (k << 5)) + 2048); }
#pragma unroll
        for (int e = 0; e < 8; e += 2) {
            stsm_x4((st2 ^ (e << 4)) + e * 128, hcmul(ge[e & 3], v[2 + (e >> 2)]), hcmul(ge[0], v[4 + (e >> 1)]), hcmul(ge[(e & 3) + 1], v[2 + (e >> 2)]), hcmul(ge[2], v[4 + (e >> 1)]));
            if (!(e & 3)) stsm_x4((st3 ^ (e << 4)) + e * 128, e ? hcmul(v[0].x, v[e]) : v[0].x, hcmul(v[0].x, v[e + 1]), hcmul(v[0].x, v[e + 2]), hcmul(v[0].x, v[e + 3]));
            mma(acc[0], af[e >> 1], b[e >> 1]);
            mma(acc[1], af[e >> 1], b[e >> 1] + 2);
        }
        __syncwarp();
        if (sel == 0x1076) CSK(3);
    }
    rest();
#pragma unroll
    for (int e = 0; e < 5; e++) k2048 += __shfl_xor_sync(~0u, k2048, 1 << e);
    {
        float* Pp = reinterpret_cast<float*>(tab + warp * 256);
        auto sw = [](int i) { return i ^ ((i >> 2) & 24); };
#pragma unroll
        for (int h = 0; h < 2; h++) {
            const int b = g + 8 * h;
            *reinterpret_cast<float2*>(Pp + sw(8 * b + 2 * t)) = make_float2(acc[0][2 * h] * unscale, acc[0][2 * h + 1] * unscale);
            *reinterpret_cast<float2*>(Pp + 128 + sw(8 * b + 2 * t)) = make_float2(acc[1][2 * h] * unscale, acc[1][2 * h + 1] * unscale);
            *reinterpret_cast<float2*>(Pp + 256 + sw(4 * b + 2 * (t & 1) + 64 * (t >> 1))) = make_float2(acc[2][2 * h] * unscale, acc[2][2 * h + 1] * unscale);
            *reinterpret_cast<float2*>(Pp + 384 + sw(2 * b + 32 * t)) = make_float2(acc[3][2 * h] * unscale, acc[3][2 * h + 1] * unscale);
            Pp[512 + sw(b + 32 * t)] = acc[4][2 * h] * unscale;
            Pp[512 + sw(b + 32 * t + 16)] = acc[4][2 * h + 1] * unscale;
        }
        if (lane == 0) Pp[640] = k2048 * unscale;
    }
    CSK(4);
    asm volatile("bar.sync %0, %1;" ::"r"(grp + 4), "r"(grp < 4 ? 64 : 96) : "memory");
    if (warp == 2) return;
    const float* Kp = reinterpret_cast<const float*>(tab);
    auto ksum = [&](int i) -> float { return rbf(Kp[i] + Kp[1024 + i] + (grp < 4 ? 0.f : Kp[2048 + i])); };
    auto ksum2 = [&](int q) -> float2 {
        q ^= (q >> 2) & 12;
        const float2 a = reinterpret_cast<const float2*>(Kp)[q], b = reinterpret_cast<const float2*>(Kp)[512 + q];
        const float2 c = grp < 4 ? make_float2(0.f, 0.f) : reinterpret_cast<const float2*>(Kp)[1024 + q];
        return make_float2(a.x + b.x + c.x, a.y + b.y + c.y);
    };
    {
        uint2* W2 = reinterpret_cast<uint2*>(in.tap + d * (TAPB / 16)) + 8;
        uint2* E4 = W2 + (TAPE - 64) / 8;
        float2 v = ksum2(64 * warp + lane), z = ksum2(64 * warp + 32 + lane), y = ksum2(128 + tid);
        const int q = (96 + tid) ^ (((96 + tid) >> 2) & 6);
        const float4 ua = reinterpret_cast<const float4*>(Kp)[q], uc = reinterpret_cast<const float4*>(Kp)[256 + q], ud = grp < 4 ? make_float4(0.f, 0.f, 0.f, 0.f) : reinterpret_cast<const float4*>(Kp)[512 + q];
        const float4 ub = make_float4(uc.x + ud.x, uc.y + ud.y, uc.z + ud.z, uc.w + ud.w);
        const float s1 = ksum(tid == 31 ? 336 : lane ? 384 : 103), s2 = ksum(tid == 31 ? 512 : tid ? 640 : 231);
        if (tid == 0) v.x += __uint_as_float(kp.pdsk << 16);
        if (tid == 63) y.y -= s1;
        const uint32_t lo = pack2(v.x, v.y), hi = pack2(z.x, z.y), tp = pack2(y.x, y.y);
        uint32_t nl = __shfl_sync(~0u, lo, lane - 1), nh = __shfl_sync(~0u, lane == 31 ? lo : hi, lane - 1), nt = __shfl_sync(~0u, tp, lane + 1);
        if (lane == 0) nl = warp ? __float_as_uint(s1) : 0u;
        if (lane == 31) nt = warp ? 0u : __float_as_uint(s1) >> 16;
        W2[64 * warp + lane] = make_uint2(__byte_perm(lo, nl, 0x7610), __byte_perm(lo, 0, 0x1032));
        W2[64 * warp + lane + 32] = make_uint2(__byte_perm(hi, nh, 0x7610), __byte_perm(hi, 0, 0x1032));
        reinterpret_cast<uint4*>(W2)[64 + tid] = make_uint4(__byte_perm(tp, __float_as_uint(s2), tid ? 0x1010 : 0x7610), __byte_perm(tp, 0, 0x1010), __byte_perm(tp, 0, 0x1032), __byte_perm(nt, tp, 0x7610));
        E4[(tid < 32 ? 159 : 209 - 32) + tid] = make_uint2(pack2(ua.x + ub.x, ua.y + ub.y), pack2(ua.z + ub.z, ua.w + ub.w - (tid == 31 ? s2 : 0.f)));
        if (tid == 63) E4[241] = make_uint2(__float_as_uint(s2) >> 16, 0u);
    }
    CSK(5);
    SPAN(0, 3);
}

#define CV_SLEEP 40
#define CV_LD "ld.relaxed.gpu.global"
#define CV_NL 1
#define CV_D2 3
#define CV_PDH 12
#define CV_PDF 4
#define CV_HAND 7
constexpr int CV_CPB = 5;
constexpr int CV_THREADS = 512;
constexpr int UPADF = 128;
constexpr int ULEN = UPADF + SEQ;
constexpr int XLEN = XCP;
constexpr int BX_5 = 0, BX_3 = 3264, BX_9 = 6528, BX_7 = 8960, BX_LEN = 11392;
constexpr int CV_SM_U = 0;
constexpr int CV_SM_T = CV_CPB * ULEN * 2;
constexpr int CV_SM_B = CV_SM_T + CV_CPB * TAPB;
constexpr int CV_SM_X = CV_SM_B + CV_CPB * BX_LEN;
constexpr int CV_SM_Y = (CV_SM_X + CV_CPB * XLEN * 2 + 127) & ~127;
constexpr int CV_SM_CNT = CV_SM_Y + CV_CPB * 8192;
constexpr int CV_SM_O = CV_SM_CNT + 128;
constexpr int CV_SMEM = CV_SM_O + 20480 + CST_EXTRA;
static_assert(ULEN % 128 == 0 && CV_SM_B % 128 == 0 && CV_SM_CNT % 128 == 0, "layout");

__device__ __forceinline__ uint32_t sub2(uint32_t x, uint32_t m) {
    const __nv_bfloat162 d = __hsub2(*reinterpret_cast<const __nv_bfloat162*>(&x), *reinterpret_cast<const __nv_bfloat162*>(&m));
    return *reinterpret_cast<const uint32_t*>(&d);
}
__device__ __forceinline__ uint32_t add2(uint32_t x, uint32_t y) {
    const __nv_bfloat162 d = __hadd2_rn(*reinterpret_cast<const __nv_bfloat162*>(&x), *reinterpret_cast<const __nv_bfloat162*>(&y));
    return *reinterpret_cast<const uint32_t*>(&d);
}
__device__ __forceinline__ void wgmma_fence() { asm volatile("wgmma.fence.sync.aligned;" ::: "memory"); }
__device__ __forceinline__ void wgmma_commit() { asm volatile("wgmma.commit_group.sync.aligned;" ::: "memory"); }
template <int N> __device__ __forceinline__ void wgmma_wait() { asm volatile("wgmma.wait_group.sync.aligned %0;" ::"n"(N) : "memory"); }
__device__ __forceinline__ uint64_t make_desc(uint32_t addr, uint32_t lbo, uint32_t sbo, uint32_t mode) {
    return (uint64_t)((addr & 0x3FFFF) >> 4) | ((uint64_t)(lbo >> 4) << 16) | ((uint64_t)(sbo >> 4) << 32) | ((uint64_t)mode << 62);
}
__device__ __forceinline__ void wgmma_rs128(float (&d)[64], uint2 hi, uint2 lo, uint64_t db, int acc) {
    asm volatile("{\n.reg .pred p;\nsetp.ne.b32 p, %69, 0;\nwgmma.mma_async.sync.aligned.m64n128k16.f32.bf16.bf16 {%0,%1,%2,%3,%4,%5,%6,%7,%8,%9,%10,%11,%12,%13,%14,%15,%16,%17,%18,%19,%20,%21,%22,%23,%24,%25,%26,%27,%28,%29,%30,%31,%32,%33,%34,%35,%36,%37,%38,%39,%40,%41,%42,%43,%44,%45,%46,%47,%48,%49,%50,%51,%52,%53,%54,%55,%56,%57,%58,%59,%60,%61,%62,%63}, {%64,%65,%66,%67}, %68, p, 1, 1, 0;\n}"
                 : "+f"(d[0]), "+f"(d[1]), "+f"(d[2]), "+f"(d[3]), "+f"(d[4]), "+f"(d[5]), "+f"(d[6]), "+f"(d[7]), "+f"(d[8]), "+f"(d[9]), "+f"(d[10]), "+f"(d[11]), "+f"(d[12]), "+f"(d[13]), "+f"(d[14]), "+f"(d[15]), "+f"(d[16]), "+f"(d[17]), "+f"(d[18]), "+f"(d[19]), "+f"(d[20]), "+f"(d[21]), "+f"(d[22]), "+f"(d[23]), "+f"(d[24]), "+f"(d[25]), "+f"(d[26]), "+f"(d[27]), "+f"(d[28]), "+f"(d[29]), "+f"(d[30]), "+f"(d[31]), "+f"(d[32]), "+f"(d[33]), "+f"(d[34]), "+f"(d[35]), "+f"(d[36]), "+f"(d[37]), "+f"(d[38]), "+f"(d[39]), "+f"(d[40]), "+f"(d[41]), "+f"(d[42]), "+f"(d[43]), "+f"(d[44]), "+f"(d[45]), "+f"(d[46]), "+f"(d[47]), "+f"(d[48]), "+f"(d[49]), "+f"(d[50]), "+f"(d[51]), "+f"(d[52]), "+f"(d[53]), "+f"(d[54]), "+f"(d[55]), "+f"(d[56]), "+f"(d[57]), "+f"(d[58]), "+f"(d[59]), "+f"(d[60]), "+f"(d[61]), "+f"(d[62]), "+f"(d[63])
                 : "r"(hi.x), "r"(hi.y), "r"(lo.x), "r"(lo.y), "l"(db), "r"(acc));
}
template <int V> struct Int { __device__ constexpr operator int() const { return V; } };
__device__ __forceinline__ void sts4(uint32_t a, const uint32_t* v) { asm volatile("st.shared.v4.u32 [%0], {%1,%2,%3,%4};" ::"r"(a), "r"(v[0]), "r"(v[1]), "r"(v[2]), "r"(v[3]) : "memory"); }
__device__ __forceinline__ uint32_t lds1(uint32_t a) { uint32_t v; asm volatile("ld.shared.u32 %0, [%1];" : "=r"(v) : "r"(a) : "memory"); return v; }
__device__ __forceinline__ uint32_t lds1v(uint32_t a) { uint32_t v; asm volatile("ld.volatile.shared.u32 %0, [%1];" : "=r"(v) : "r"(a) : "memory"); return v; }
__device__ __forceinline__ uint4 lds4(uint32_t a) { uint4 v; asm volatile("ld.shared.v4.u32 {%0,%1,%2,%3}, [%4];" : "=r"(v.x), "=r"(v.y), "=r"(v.z), "=r"(v.w) : "r"(a) : "memory"); return v; }
__device__ __forceinline__ uint4 ldx(uint32_t a) {
    uint4 v;
    asm volatile("ld.shared.v2.u32 {%0,%1}, [%4];\nld.shared.v2.u32 {%2,%3}, [%4+128];" : "=r"(v.x), "=r"(v.y), "=r"(v.z), "=r"(v.w) : "r"(a) : "memory");
    return v;
}
__device__ __forceinline__ void cv_store(unsigned char* p, uint4 x, uint4 y) {
    asm volatile("st.relaxed.gpu.global.v2.u32 [%0], {%1,%2};" ::"l"(p), "r"(add2(x.x, __byte_perm(y.x, y.y, 0x5410))), "r"(add2(x.y, __byte_perm(y.z, y.w, 0x5410))) : "memory");
    asm volatile("st.relaxed.gpu.global.v2.u32 [%0], {%1,%2};" ::"l"(p + 128), "r"(add2(x.z, __byte_perm(y.x, y.y, 0x7632))), "r"(add2(x.w, __byte_perm(y.z, y.w, 0x7632))) : "memory");
}
__device__ __forceinline__ int usw(int ch) { return ch ^ ((ch >> 3) & 1); }
__global__ void __launch_bounds__(CV_THREADS, 1) conv_kernel(int layer, const uint4* __restrict__ piv, const float4* __restrict__ sum, const bf16* __restrict__ x1T,
                                                             bf16* __restrict__ dst, const uint4* __restrict__ tap, const __grid_constant__ CUtensorMap tmOut) {
    extern __shared__ __align__(1024) unsigned char sm[];
    SPAN(3 + 4 * layer, 0);
    bf16* Us = reinterpret_cast<bf16*>(sm + CV_SM_U);
    bf16* Xs = reinterpret_cast<bf16*>(sm + CV_SM_X);
#define CV_IDX int tid; asm volatile("mov.u32 %0, %tid.x;" : "=r"(tid)); const int lane = tid & 31, warp = __shfl_sync(~0u, tid >> 5, 0);
    const int d0 = blockIdx.x * CV_CPB, tile = blockIdx.x; (void)tile;
    const uint32_t cnt = smem_u32(sm + CV_SM_CNT);
    struct Lc { uint32_t a4, a8, uc, ud, y, e4, en, sp, ss; int go; };
    auto lane_consts = [&](int lane, int c) {
        const int mat = lane >> 3, r = lane & 7, g = lane >> 2, ti = lane & 3, e = g - 2 * ti;
        const int j2 = 13 + (r ^ 1) + 8 * (mat >> 1), j3 = j2 + 2, i0 = 8 * (mat & 1);
        const uint32_t sb = smem_u32(sm), oc = sb + usw(16 * (mat >> 1) + 2 * r + (mat & 1)) * 16;
        const Lc l = {sb + CV_SM_B + c * BX_LEN + ((j2 & 1) ? BX_3 + (4 * j2 + i0 + 84) * 2 : BX_5 + (4 * j2 + i0 + 80) * 2),
                      sb + CV_SM_B + c * BX_LEN + ((j3 & 1) ? BX_7 : BX_9) + (8 * j3 + i0 + 136) * 2,
                      oc + CV_SM_U + (c * ULEN + UPADF) * 2, sb + CV_SM_U + (c * ULEN + UPADF) * 2 + usw(16 * mat + 2 * r + 2) * 16, oc + CV_SM_Y + c * 8192,
                      sb + CV_SM_T + c * TAPB + TAPE + (307 + 2 * g - ti) * 4, sb + CV_SM_T + c * TAPB + (528 + e) * 4,
                      e == -5 ? 0x4410u : e == -4 ? 0x1044u : 0x4444u, e == 3 ? 0x4410u : e == 4 ? 0x1044u : 0x4444u,
                      c * XCP * 2 + (lane >> 4) * 256 + (lane & 15) * 8};
        asm volatile("st.shared.u32 [%0], %1;" ::"r"(sb + CV_SM_CNT + 120), "r"(l.y ^ l.a4 ^ l.a8 ^ l.uc ^ l.ud ^ l.e4 ^ l.en ^ l.sp ^ l.ss ^ l.go) : "memory");
        return l;
    };
    unsigned char* const dq = reinterpret_cast<unsigned char*>(dst + (size_t)d0 * XCP);
    auto far = [&](auto T0_, const auto& seq, const Lc& lc, int c, int lane, const uint2 (&f)[20], uint32_t kk) {
        constexpr int T0 = T0_, T1 = T0 + 6, TC = T0 > 7 ? T0 : 7, NS = sizeof(seq) / sizeof(seq[0]), PD = T0 > 7 ? CV_PDH : CV_PDF;
        uint32_t bq[28], yw[4], yz[4], P, S;
        uint4 xv, yv;
        asm("prmt.b32 %0, %1, 0, %2;" : "=r"(P) : "r"(kk), "r"(lc.sp));
        asm("prmt.b32 %0, %1, 0, %2;" : "=r"(S) : "r"(kk), "r"(lc.ss));
#pragma unroll
        for (int k = 0; 2 * k < T1 - TC + 4; k++) ldsm_x4(bq + 4 * k, lc.uc + (TC - 8) * 256 + 512 * k);
#pragma unroll
        for (int k = 0; 4 * k < T1 - TC; k++) ldsm_x4(bq + 20 + 4 * k, lc.ud + (TC - 8) * 256 + 1024 * k);
        CST(3);
        mbar_wait(cnt + 8 * c, 0);
        mbar_wait(cnt + 40, 0);
        CST(4);
        float acc[6][4] = {};
        uint32_t a[PD + 1][4];
#pragma unroll
        for (int i = -PD; i < NS + 3; i++) {
            if (i + PD < NS) ldsm_x4_t(a[(i + PD) % (PD + 1)], seq[i + PD] < 32 ? lc.a4 + (seq[i + PD] - 2) * 128 : lc.a8 + (seq[i + PD] - 34) * 256);
            if (i < 0) continue;
#pragma unroll
            for (int T = T0; T < T1; T++) {
                if (i >= NS) break;
                const int ee = seq[i] < 32 ? 2 * T - 6 - seq[i] : T + 35 - seq[i];
                if (i == 0 && T >= TC) mma_bf16(acc[T - T0], P, 0u, S, P, bq[2 * (T - TC)], bq[2 * (T - TC) + 1]);
                if (i == 1 && T >= TC) mma_bf16_k8(acc[T - T0], 0u, S, bq[20 + T - TC]);
                if (i == (T >= TC ? 2 : 0)) mma_bf16(acc[T - T0], f[19].x, 0u, f[19].y, f[19].x, bq[2 * (T - TC + 4)], bq[2 * (T - TC + 4) + 1]);
                if (seq[i] < 32 ? ee >= 0 && ee <= 9 : ee >= 10) mma_bf16(acc[T - T0], a[i % (PD + 1)][0], a[i % (PD + 1)][1], a[i % (PD + 1)][2], a[i % (PD + 1)][3], f[ee].x, f[ee].y);
            }
#pragma unroll
            for (int k = 0; k < 3; k++) {
                const int o = 256 * T0 + 512 * k;
                auto at = [&](int d) { return i - d >= 0 && i - d < NS && seq[i - d < 0 ? 0 : i - d < NS ? i - d : 0] == 2 * T0 + 4 * k - 4; };
                if (at(CV_D2)) {
                    cv_store(dq + lc.go + o, xv, yv);
                    if (layer > 19 - 2 * k) __trap();
                }
                if (at(-2)) { ldsm_x4_t(yw, lc.y + o); ldsm_x4_t(yz, lc.y + 3584 + o); }
                if (at(1)) {
#pragma unroll
                    for (int q = 0; q < 4; q++) yw[q] = add2(add2(yw[q], yz[q]), pack2(acc[2 * k + (q >> 1)][2 * (q & 1)], acc[2 * k + (q >> 1)][2 * (q & 1) + 1]));
                    stsm_x4_t(lc.y + o, yw[0], yw[1], yw[2], yw[3]);
                    xv = ldx(smem_u32(Xs) + lc.go + o);
                    __syncwarp();
                    yv = lds4(smem_u32(sm + CV_SM_Y) + c * 8192 + o + usw(lane) * 16);
                    if (layer > 20 - 2 * k) __trap();
                    if (k == 2) CST(6);
                }
            }
        }
    };
    TSTAMP1X(9, 256);
    if (threadIdx.x >= 256) {
        if (threadIdx.x < 288 && elect()) {
            mbar_init(cnt + 48, 1);
            asm volatile("fence.mbarrier_init.release.cluster;" ::: "memory");
            bulk_load(smem_u32(sm + CV_SM_T), tap + d0 * (TAPB / 16), CV_CPB * TAPB, cnt + 48);
            mbar_expect_tx(cnt + 48, CV_CPB * TAPB);
        }
        CV_IDX
        const int wgu = (warp >> 2) & 1, g = lane >> 2, ti = lane & 3;
        CST(1);
        if (warp > 8 && elect()) {
            if (warp < 15) mbar_init(cnt + 8 * (warp - 9), warp == 14 ? 8 : 4);
            else if (layer) prefetch_tmap(&tmOut);
        }
        if (warp < 13 && lane < 17 - (warp == 12)) {
            const int off = warp == 12 ? CV_SM_U : CV_SM_B + (warp == 11 ? BX_7 : (warp - 8) * BX_3), str = warp == 12 ? ULEN * 2 : BX_LEN;
#pragma unroll
            for (int c = 0; c < CV_CPB; c++) *reinterpret_cast<uint4*>(sm + off + c * str + 16 * lane) = make_uint4(0, 0, 0, 0);
        }
        fence_async_smem();
        asm volatile("bar.arrive 3, 512;" ::: "memory");
        asm volatile("bar.sync 1, 256;" ::: "memory");
        TSTAMP1X(10, 256);
        asm volatile("setmaxnreg.inc.sync.aligned.u32 168;");
        const uint32_t Tc = smem_u32(sm + CV_SM_T) + (16 + 128 * (warp & 2) + 8 * (warp & 1) + g - 2 * ti) * 4;
        uint2 fa[8][2], fn[8][2];
        auto near_taps = [&](uint2 (&f)[8][2], int c) {
#pragma unroll
            for (int m = 0; m < 16; m++) f[m >> 1][m & 1] = make_uint2(lds1v(Tc + c * TAPB + 64 * (m >> 1) - 32 * (m & 1)), lds1v(Tc + c * TAPB + 64 * (m >> 1) - 32 * (m & 1) + 512));
        };
        CST(6);
        mbar_wait(cnt + 48, 0);
        TSTAMP1X(11, 256); CST(5);
        near_taps(fa, 3 * wgu);
        near_taps(fn, 2 - wgu);
        const int hc = wgu ? warp & 3 : 4;
        const Lc lc = lane_consts(lane, hc);
        TSTAMP1X(12, 256); CST(0);
        uint32_t ya = smem_u32(sm + CV_SM_Y) + wgu * 8192 + (warp & 2) * 2048 + usw(2 * lane + (warp & 1)) * 16;
        uint64_t db = make_desc(smem_u32(Us + wgu * ULEN + UPADF), 16, 256, 3);
        if (wgu) { asm volatile("bar.sync 6, 384;" ::: "memory"); fence_async_smem(); }
        int c = wgu;
        auto chain = [&](const uint2 (&f)[8][2], auto&& meanwhile) {
            float acc[64];
            asm volatile("bar.sync %0, %1;" ::"r"(c ? 4 + wgu : 2), "r"(c ? 256 : 384) : "memory");
            TSTAMPC(1 + 3 * c);
            if (c < 2) CST(7);
            if (c == 0) fence_async_smem();
            wgmma_fence();
#pragma unroll
            for (int m = 0; m < 8; m++) {
                wgmma_rs128(acc, f[m][0], f[m][1], db - (uint64_t)(2 * m), m);
                if (m == CV_HAND && c < 4) asm volatile("bar.arrive %0, 256;" ::"r"(5 - wgu) : "memory");
            }
            wgmma_commit();
            asm volatile("griddepcontrol.launch_dependents;" ::: "memory");
            TSTAMPC(2 + 3 * c); CST(13 + (c >> 1));
            meanwhile();
            wgmma_wait<0>();
            TSTAMPC(3 + 3 * c); CST(10 + (c >> 1));
            uint32_t w[16];
#pragma unroll
            for (int j = 0; j < 16; j++) w[j] = j ? pack2(acc[4 * j] + acc[4 * j - 2], acc[4 * j + 1] + acc[4 * j - 1]) : pack2(acc[0], acc[1]);
#pragma unroll
            for (int j = 0; j < 16; j += 4) stsm_x4_t(ya + 256 * j, w[j], w[j + 1], w[j + 2], w[j + 3]);
            __syncwarp();
            if (lane == 0) mbar_arrive(cnt + 8 * c);
            c += 2; ya += 16384; db += ULEN / 4;
        };
        const uint32_t e4 = lc.e4, e8 = e4 + 428 - 4 * g;
        uint2 fl[4];
        uint32_t kk;
#pragma unroll 1
        for (;;) {
            if (c != 1) chain(fa, [&] {
                if (c == 3 || warp + c == 12) {
#pragma unroll
                    for (int k = 0; k < 19; k++) (k < 16 ? fn[(k >> 1) & 7][k & 1] : fl[k & 3]) = make_uint2(lds1(k < 10 ? e4 + 32 * k + 16 : e8 + 32 * k - 304), lds1(k < 10 ? e4 + 32 * k : e8 + 32 * k - 320));
                    fl[3] = make_uint2(lds1(lc.en), lds1(lc.en - 32));
                    kk = lds1(smem_u32(sm + CV_SM_T) + TAPB * hc + TAPE + 1672);
                }
            });
            if (c > 4) break;
            if (c == 2) { asm volatile("bar.sync 7, 384;" ::: "memory"); fence_async_smem(); }
            chain(fn, [&] { if (c == 2) near_taps(fa, 4); });
        }
        TSTAMP1X(6, 256); CST(2);
        if (wgu || warp == 8) {
            constexpr int seq[29] = {5, 6, 32, 7, 33, 8, 34, 9, 35, 10, 36, 11, 12, 13, 14, 15, 16, 17, 37, 18, 38, 19, 20, 21, 39, 22, 40, 23, 24};
            uint2 f[20];
#pragma unroll
            for (int k = 0; k < 20; k++) f[k] = k < 16 ? fn[(k >> 1) & 7][k & 1] : fl[k & 3];
            far(Int<10>(), seq, lc, hc, lane, f, kk);
        }
    } else {
        asm volatile("setmaxnreg.dec.sync.aligned.u32 88;");
        CV_IDX
        CST(5);
        const uint4* ppv = piv + tid;
        const float4* psv = sum + tid;
        const uint2* pxv = reinterpret_cast<const uint2*>(x1T + (size_t)d0 * XCP) + (tid >> 4) * 32 + (tid & 15);
        asm volatile("st.shared.u64 [%0], %1;" ::"r"(smem_u32(sm + CV_SM_O) + tid * 16), "l"((uint64_t)ppv ^ (uint64_t)psv ^ (uint64_t)pxv) : "memory");
        const int tc = (0x04302100 >> (4 * warp)) & 7;
        const Lc lc = lane_consts(lane, tc);
        pdl_sync();
        SPAN(3 + 4 * layer, 1);
        TSTAMP(0); CST(0);
        if (tid == 0) TSTAMPC(0);
        if (threadIdx.x == 0) { GSTAMP(g_tim, 15); }
        float4 sv[4];
        uint4 pv;
#pragma unroll
        for (int k = 0; k < 4; k++)
            asm volatile(CV_LD ".v4.f32 {%0,%1,%2,%3}, [%4];" : "=f"(sv[k].x), "=f"(sv[k].y), "=f"(sv[k].z), "=f"(sv[k].w) : "l"(psv + 256 * k) : "memory");
        asm volatile(CV_LD ".v4.u32 {%0,%1,%2,%3}, [%4];" : "=r"(pv.x), "=r"(pv.y), "=r"(pv.z), "=r"(pv.w) : "l"(ppv) : "memory");
        uint2 xe[CV_CPB], xo[CV_CPB];
#pragma unroll
        for (int c = 0; c < CV_NL; c++) {
            asm volatile(CV_LD ".v2.u32 {%0,%1}, [%2];" : "=r"(xe[c].x), "=r"(xe[c].y) : "l"(pxv + c * (XCP / 4)) : "memory");
            asm volatile(CV_LD ".v2.u32 {%0,%1}, [%2];" : "=r"(xo[c].x), "=r"(xo[c].y) : "l"(pxv + c * (XCP / 4) + 16) : "memory");
        }
#define CV_XD 300
#define CV_XW 0
        if (warp == CV_XW) {
            if (elect()) {
                const uint32_t c0 = clock();
                mbar_init(cnt + 56, 1);
                asm volatile("fence.mbarrier_init.release.cluster;" ::: "memory");
                mbar_expect_tx(cnt + 56, CV_CPB * 4096);
                while (clock() - c0 < CV_XD) ;
#pragma unroll
                for (int c = CV_NL; c < CV_CPB + CV_NL; c++) bulk_load(smem_u32(Xs + (c % CV_CPB) * XLEN), x1T + (size_t)(d0 + c % CV_CPB) * XCP, 4096, cnt + 56);
            }
            __syncwarp();
            CST(15);
        }
        constexpr float idm = 1.0f / DM;
        uint32_t mw[4];
        float rs[8];
#pragma unroll
        for (int k = 0; k < 4; k++) {
            const uint32_t pw = k == 0 ? pv.x : k == 1 ? pv.y : k == 2 ? pv.z : pv.w;
            mw[k] = pack2(fmaf(sv[k].x, idm, __uint_as_float(pw << 16)), fmaf(sv[k].z, idm, __uint_as_float(pw & 0xffff0000u)));
            uint32_t vr;
            asm("cvt.rn.relu.bf16x2.f32 %0, %1, %2;" : "=r"(vr) : "f"(fmaf(sv[k].z * -idm, sv[k].z, sv[k].w) * idm), "f"(fmaf(sv[k].x * -idm, sv[k].x, sv[k].y) * idm));
            const uint32_t ve = pack2(__uint_as_float(vr << 16) + 1e-5f, __uint_as_float(vr & 0xffff0000u) + 1e-5f);
            const uint32_t sd = pack2(sqrt_apx(__uint_as_float(ve << 16)), sqrt_apx(__uint_as_float(ve & 0xffff0000u)));
            rs[2 * k] = rcp_apx(__uint_as_float(sd << 16)); rs[2 * k + 1] = rcp_apx(__uint_as_float(sd & 0xffff0000u));
        }
        if (rs[0] != 123.f) TSTAMP(13);
        const uint32_t ua = smem_u32(Us) + usw(tid + UPADF / 8) * 16;
        uint32_t uw[CV_CPB][4];
#pragma unroll
        for (int c = 0; c < CV_CPB; c++) {
            if (c == CV_NL) {
                if (warp == CV_XW) { mbar_wait(cnt + 56, 0); CST(7); }
                asm volatile("bar.sync 10, 256;" ::: "memory");
            }
            if (c == 1 || c == 2) {
#pragma unroll
                for (int k = c; k < (c == 1 ? 2 : CV_CPB); k++) {
 const uint4 v = ldx(smem_u32(Xs + k * XLEN) + (tid >> 4) * 256 + (tid & 15) * 8); xe[k] = make_uint2(v.x, v.y); xo[k] = make_uint2(v.z, v.w); }
            }
            const uint32_t e0 = sub2(xe[c].x, mw[0]), e1 = sub2(xe[c].y, mw[1]), o0 = sub2(xo[c].x, mw[2]), o1 = sub2(xo[c].y, mw[3]);
            uw[c][0] = pack2(__uint_as_float(e0 << 16) * rs[0], __uint_as_float(o0 << 16) * rs[4]); uw[c][1] = pack2(__uint_as_float(e0 & 0xffff0000u) * rs[1], __uint_as_float(o0 & 0xffff0000u) * rs[5]);
            uw[c][2] = pack2(__uint_as_float(e1 << 16) * rs[2], __uint_as_float(o1 << 16) * rs[6]); uw[c][3] = pack2(__uint_as_float(e1 & 0xffff0000u) * rs[3], __uint_as_float(o1 & 0xffff0000u) * rs[7]);
            asm volatile("st.shared.v4.u32 [%0], {%1,%2,%3,%4};" ::"r"(ua + c * ULEN * 2), "r"(uw[c][0]), "r"(uw[c][1]), "r"(uw[c][2]), "r"(uw[c][3]) : "memory");
            if (c < 2) {
                asm volatile("bar.arrive %0, 384;" ::"r"(2 + 4 * c) : "memory");
                if (layer > 29 - c) __trap();
                CST(11 + c);
            }
        }
        asm volatile("bar.arrive 7, 384;" ::: "memory");
        asm volatile("bar.sync 3, 512;" ::: "memory");
        TSTAMP(1); CST(1);
        {
            auto box = [&](auto c0, auto c1, int chunk, int cb, bool full) {
                const uint32_t ea = smem_u32(Us + cb * ULEN) + usw(chunk + UPADF / 8 + (lane ? 1 : -1)) * 16, bx = smem_u32(sm + CV_SM_B + cb * BX_LEN) + chunk * 16;
                uint32_t lo[CV_CPB][4], hi[CV_CPB][2];
#pragma unroll
                for (int c = c0; c < c1; c++) {
                    lo[c][0] = 0;
#pragma unroll
                    for (int k = 1; k < 4; k++) lo[c][k] = __shfl_up_sync(~0u, uw[c][k], 1);
#pragma unroll
                    for (int k = 0; k < 2; k++) hi[c][k] = __shfl_down_sync(~0u, uw[c][k], 1);
                }
#pragma unroll
                for (int c = c0; c < c1; c++)
                    asm volatile("{\n.reg .pred p, q;\nsetp.eq.s32 p, %7, 0;\nsetp.eq.s32 q, %7, 31;\n@p ld.shared.v4.u32 {%0,%1,%2,%3}, [%6];\n@q ld.shared.v2.u32 {%4,%5}, [%6];\n}"
                                 : "+r"(lo[c][0]), "+r"(lo[c][1]), "+r"(lo[c][2]), "+r"(lo[c][3]), "+r"(hi[c][0]), "+r"(hi[c][1]) : "r"(ea + c * ULEN * 2), "r"(lane) : "memory");
#pragma unroll
                for (int c = c0; c < c1; c++) {
                    const uint32_t e[9] = {lo[c][1], lo[c][2], lo[c][3], uw[c][0], uw[c][1], uw[c][2], uw[c][3], hi[c][0], hi[c][1]};
                    uint32_t o[8], p[8], t[7], b3[5], b5[7];
#pragma unroll
                    for (int i = 0; i < 8; i++) { o[i] = __byte_perm(e[i], e[i + 1], 0x5432); p[i] = add2(e[i], o[i]); }
#pragma unroll
                    for (int i = 0; i < 5; i++) b3[i] = add2(o[i], p[i + 1]);
                    sts4(bx + c * BX_LEN + BX_3 + 160, b3);
#pragma unroll
                    for (int i = 1; i < 7; i++) { t[i] = add2(p[i], p[i + 1]); b5[i] = add2(t[i], e[i + 2]); }
                    sts4(bx + c * BX_LEN + BX_5 + 160, b5 + 2);
                    if (full) {
#pragma unroll
                        for (int i = 1; i < 5; i++) { b3[i] = add2(b3[i], t[i + 2]); t[i] = add2(t[i], b5[i + 2]); }
                        sts4(bx + c * BX_LEN + BX_7 + 272, b3 + 1);
                        sts4(bx + c * BX_LEN + BX_9 + 272, t + 1);
                    }
                }
            };
            auto reload = [&](int c, uint32_t a) { const uint4 v = lds4(a); uw[c][0] = v.x; uw[c][1] = v.y; uw[c][2] = v.z; uw[c][3] = v.w; };
            if (warp >= 6) {
#pragma unroll
                for (int c = 0; c < 3; c++) reload(c, ua - 1024 + (c + 2) * ULEN * 2);
            }
            if (warp >= 4) {
#pragma unroll
                for (int c = 3; c < 5; c++) reload(c, ua - 2048 + c * ULEN * 2);
            }
            box(Int<0>(), Int<3>(), warp < 6 ? tid : tid - 64, warp < 6 ? 0 : 2, warp < 4);
            if (warp >= 4) box(Int<3>(), Int<5>(), tid - 128, 0, true);
            else if (tid >= 128 - CV_CPB) {
                const int c = 127 - tid;
                const uint2 v = *reinterpret_cast<const uint2*>(Us + c * ULEN + UPADF);
                const float s1 = __uint_as_float(v.x << 16), s2 = s1 + __uint_as_float(v.x & 0xffff0000u), s3 = s2 + __uint_as_float(v.y << 16), s4 = s3 + __uint_as_float(v.y & 0xffff0000u);
                unsigned char* bc = sm + CV_SM_B + c * BX_LEN;
                *reinterpret_cast<uint32_t*>(bc + BX_5 + 156) = pack2(s1, s2);
                *reinterpret_cast<uint2*>(bc + BX_7 + 264) = make_uint2(v.x << 16, pack2(s2, s3));
                *reinterpret_cast<uint2*>(bc + BX_9 + 264) = make_uint2(pack2(s1, s2), pack2(s3, s4));
            }
        }
        __syncwarp();
        if (lane == 0) mbar_arrive(cnt + 40);
        TSTAMP(2); CST(2);
        if (layer && blockIdx.x == 0 && tid == 224) g_epoch = ld_epoch();
        __syncwarp();
        if ((0x6e >> warp) & 1) {
            constexpr int seq[16] = {0, 1, 2, 3, 4, 5, 6, 32, 7, 8, 9, 33, 10, 34, 11, 12};
            uint2 f[20];
            mbar_wait(cnt, 0);
            const uint32_t e8 = lc.e4 + 428 - (lane & 28);
#pragma unroll
            for (int k = 0; k < 13; k++) f[k] = make_uint2(lds1(k < 10 ? lc.e4 + 32 * k + 16 : e8 + 32 * k - 304), lds1(k < 10 ? lc.e4 + 32 * k : e8 + 32 * k - 320));
            f[19] = make_uint2(lds1(lc.en), lds1(lc.en - 32));
            far(Int<4>(), seq, lc, tc, lane, f, lds1(smem_u32(sm + CV_SM_T) + TAPB * tc + TAPE + 1672));
        }
    }
    {
        CV_IDX
        if ((0xc91 >> warp) & 1) {
            const int c = __popc(0xc91 & ((1 << warp) - 1));
            uint4 xv[2], yv[2];
#pragma unroll
            for (int k = 0; k < 2; k++) xv[k] = ldx(smem_u32(Xs + c * XLEN) + 512 * k + (lane >> 4) * 256 + (lane & 15) * 8);
            const uint32_t u0 = lds1(smem_u32(Us + c * ULEN) + (lane == 31 ? UPADF * 2 : 0));
            mbar_wait(cnt + 8 * c, 0);
#pragma unroll
            for (int k = 0; k < 2; k++) yv[k] = lds4(smem_u32(sm + CV_SM_Y) + c * 8192 + 512 * k + usw(lane) * 16);
            const uint4 yz = lds4(smem_u32(sm + CV_SM_Y) + c * 8192 + 4096 + usw(lane) * 16);
            const float kk = __uint_as_float(lds1(smem_u32(sm + CV_SM_T) + TAPB * c + TAPE + 1272) << 16);
            yv[1].x = add2(yv[1].x, yz.x); yv[1].y = add2(yv[1].y, yz.y); yv[1].z = add2(yv[1].z, yz.z);
            yv[1].w = pack2(fmaf(kk, __uint_as_float(u0 << 16), __uint_as_float(yv[1].w << 16) + __uint_as_float(yz.w << 16)),
                            fmaf(kk, __uint_as_float(u0 << 16) + __uint_as_float(u0 & 0xffff0000u), __uint_as_float(yv[1].w & 0xffff0000u) + __uint_as_float(yz.w & 0xffff0000u)));
#pragma unroll
            for (int k = 0; k < 2; k++) cv_store(dq + c * XCP * 2 + (lane >> 4) * 256 + (lane & 15) * 8 + 512 * k, xv[k], yv[k]);
        }
        TSTAMP(4); CST(8);
        if (layer == 1) {
            const int rb = (blockIdx.x >> 3) + (warp & 8) * 2, cg = blockIdx.x & 7, ch = (tid >> 3) & 31;
            const bf16* src = dst + (size_t)(cg * 80 + ch) * XCP + rb * 64 + (tid & 7) * 8;
            uint32_t v[3][4];
            __syncthreads();
            if (warp & 8) { const uint32_t c0 = clock(); while (clock() - c0 < 300) ; }
            uint32_t todo = (warp & 4) ? 3 : 7;
#pragma unroll 1
            for (int it = 0; it < SPIN_MAX; it++) {
#pragma unroll
                for (int k = 0; k < 3; k++)
                    if (todo >> k & 1)
                        asm volatile("ld.relaxed.gpu.global.v4.u32 {%0,%1,%2,%3}, [%4];" : "=r"(v[k][0]), "=r"(v[k][1]), "=r"(v[k][2]), "=r"(v[k][3]) : "l"(src + k * (32 * XCP)) : "memory");
#pragma unroll
                for (int k = 0; k < 3; k++)
                    if ((todo >> k & 1) && v[k][0] != ~0u && v[k][1] != ~0u && v[k][2] != ~0u && v[k][3] != ~0u) {
                        *reinterpret_cast<uint4*>(sm + (32 * k + ch) * 272 + ((tid & 7) + (warp & 8)) * 16) = make_uint4(v[k][0], v[k][1], v[k][2], v[k][3]);
                        todo ^= 1u << k;
                    }
                if (!todo) break;
                __nanosleep(CV_SLEEP);
            }
            __syncwarp();
            asm volatile("bar.sync %0, 256;" ::"r"(8 + (warp >> 3)) : "memory");
            uint32_t w[12];
#pragma unroll
            for (int k = 0; k < 3; k++) ldsm_x4(&w[4 * k], smem_u32(sm) + min(32 * k + lane, 79) * 272 + warp * 16);
            const uint32_t ot = smem_u32(sm + CV_SM_O) + warp * 1280, oa = ot + (lane & 7) * 160 + (lane >> 3) * 16;
            stsm_x4_t(oa, w[0], w[1], w[2], w[3]);
            stsm_x4_t(oa + 64, w[4], w[5], w[6], w[7]);
            asm volatile("stmatrix.sync.aligned.m8n8.x2.trans.shared.b16 [%0], {%1,%2};" ::"r"(oa + 128), "r"(w[8]), "r"(w[9]) : "memory");
            fence_async_smem();
            __syncwarp();
            if (lane == 0) {
                asm volatile("cp.async.bulk.tensor.3d.global.shared::cta.bulk_group [%0, {%1, %2, %3}], [%4];" ::"l"(&tmOut), "r"(cg * 80), "r"((rb >> 1) * 64 + 8 * (warp & 7)), "r"(rb & 1), "r"(ot) : "memory");
                asm volatile("cp.async.bulk.commit_group;" ::: "memory");
                asm volatile("cp.async.bulk.wait_group.read 0;" ::: "memory");
            }
        }
    }
    TSTAMP(3); CST(9); CST_END;
    GSTAMP(g_tim, 14);
    SPAN(3 + 4 * layer, 3);
}

template <int TA, int TB>
__device__ __forceinline__ void wgmma_n240(float (&d)[120], uint64_t da, uint64_t db, int acc) {
    asm volatile("{\n.reg .pred p;\nsetp.ne.b32 p, %124, 0;\nwgmma.mma_async.sync.aligned.m64n240k16.f32.bf16.bf16 {%0,%1,%2,%3,%4,%5,%6,%7,%8,%9,%10,%11,%12,%13,%14,%15,%16,%17,%18,%19,%20,%21,%22,%23,%24,%25,%26,%27,%28,%29,%30,%31,%32,%33,%34,%35,%36,%37,%38,%39,%40,%41,%42,%43,%44,%45,%46,%47,%48,%49,%50,%51,%52,%53,%54,%55,%56,%57,%58,%59,%60,%61,%62,%63,%64,%65,%66,%67,%68,%69,%70,%71,%72,%73,%74,%75,%76,%77,%78,%79,%80,%81,%82,%83,%84,%85,%86,%87,%88,%89,%90,%91,%92,%93,%94,%95,%96,%97,%98,%99,%100,%101,%102,%103,%104,%105,%106,%107,%108,%109,%110,%111,%112,%113,%114,%115,%116,%117,%118,%119}, %120, %121, p, 1, 1, %122, %123;\n}"
                 : "+f"(d[0]), "+f"(d[1]), "+f"(d[2]), "+f"(d[3]), "+f"(d[4]), "+f"(d[5]), "+f"(d[6]), "+f"(d[7]), "+f"(d[8]), "+f"(d[9]), "+f"(d[10]), "+f"(d[11]), "+f"(d[12]), "+f"(d[13]), "+f"(d[14]), "+f"(d[15]), "+f"(d[16]), "+f"(d[17]), "+f"(d[18]), "+f"(d[19]), "+f"(d[20]), "+f"(d[21]), "+f"(d[22]), "+f"(d[23]), "+f"(d[24]), "+f"(d[25]), "+f"(d[26]), "+f"(d[27]), "+f"(d[28]), "+f"(d[29]), "+f"(d[30]), "+f"(d[31]), "+f"(d[32]), "+f"(d[33]), "+f"(d[34]), "+f"(d[35]), "+f"(d[36]), "+f"(d[37]), "+f"(d[38]), "+f"(d[39]), "+f"(d[40]), "+f"(d[41]), "+f"(d[42]), "+f"(d[43]), "+f"(d[44]), "+f"(d[45]), "+f"(d[46]), "+f"(d[47]), "+f"(d[48]), "+f"(d[49]), "+f"(d[50]), "+f"(d[51]), "+f"(d[52]), "+f"(d[53]), "+f"(d[54]), "+f"(d[55]), "+f"(d[56]), "+f"(d[57]), "+f"(d[58]), "+f"(d[59]), "+f"(d[60]), "+f"(d[61]), "+f"(d[62]), "+f"(d[63]), "+f"(d[64]), "+f"(d[65]), "+f"(d[66]), "+f"(d[67]), "+f"(d[68]), "+f"(d[69]), "+f"(d[70]), "+f"(d[71]), "+f"(d[72]), "+f"(d[73]), "+f"(d[74]), "+f"(d[75]), "+f"(d[76]), "+f"(d[77]), "+f"(d[78]), "+f"(d[79]), "+f"(d[80]), "+f"(d[81]), "+f"(d[82]), "+f"(d[83]), "+f"(d[84]), "+f"(d[85]), "+f"(d[86]), "+f"(d[87]), "+f"(d[88]), "+f"(d[89]), "+f"(d[90]), "+f"(d[91]), "+f"(d[92]), "+f"(d[93]), "+f"(d[94]), "+f"(d[95]), "+f"(d[96]), "+f"(d[97]), "+f"(d[98]), "+f"(d[99]), "+f"(d[100]), "+f"(d[101]), "+f"(d[102]), "+f"(d[103]), "+f"(d[104]), "+f"(d[105]), "+f"(d[106]), "+f"(d[107]), "+f"(d[108]), "+f"(d[109]), "+f"(d[110]), "+f"(d[111]), "+f"(d[112]), "+f"(d[113]), "+f"(d[114]), "+f"(d[115]), "+f"(d[116]), "+f"(d[117]), "+f"(d[118]), "+f"(d[119])
                 : "l"(da), "l"(db), "n"(TA), "n"(TB), "r"(acc));
}

__device__ __forceinline__ void wgmma_n80(float (&d)[40], uint64_t da, uint64_t db, int acc) {
    asm volatile("{\n.reg .pred p;\nsetp.ne.b32 p, %42, 0;\nwgmma.mma_async.sync.aligned.m64n80k16.f32.bf16.bf16 {%0,%1,%2,%3,%4,%5,%6,%7,%8,%9,%10,%11,%12,%13,%14,%15,%16,%17,%18,%19,%20,%21,%22,%23,%24,%25,%26,%27,%28,%29,%30,%31,%32,%33,%34,%35,%36,%37,%38,%39}, %40, %41, p, 1, 1, 0, 1;\n}"
                 : "+f"(d[0]), "+f"(d[1]), "+f"(d[2]), "+f"(d[3]), "+f"(d[4]), "+f"(d[5]), "+f"(d[6]), "+f"(d[7]), "+f"(d[8]), "+f"(d[9]), "+f"(d[10]), "+f"(d[11]), "+f"(d[12]), "+f"(d[13]), "+f"(d[14]), "+f"(d[15]), "+f"(d[16]), "+f"(d[17]), "+f"(d[18]), "+f"(d[19]), "+f"(d[20]), "+f"(d[21]), "+f"(d[22]), "+f"(d[23]), "+f"(d[24]), "+f"(d[25]), "+f"(d[26]), "+f"(d[27]), "+f"(d[28]), "+f"(d[29]), "+f"(d[30]), "+f"(d[31]), "+f"(d[32]), "+f"(d[33]), "+f"(d[34]), "+f"(d[35]), "+f"(d[36]), "+f"(d[37]), "+f"(d[38]), "+f"(d[39])
                 : "l"(da), "l"(db), "r"(acc));
}

constexpr int A1_THREADS = 384;
constexpr int A1_NST = 4;
#define A1_SKEW 8
constexpr int A1_STAGE = 16384 + WQ_STAGE;
constexpr int A1_KVP = 336;
constexpr int A1_SM_KV = 2 * A1_STAGE;
constexpr int A1_SM_END = A1_NST * A1_STAGE;
constexpr int A1_SM_BAR = A1_SM_END + 3072 + 3 * WOB + 64;
constexpr int A1_SM_RS = A1_SM_END + 512;
constexpr int A1_SM_W0 = A1_SM_END + 3072, A1_SM_W3 = A1_SM_END - 3 * WOB, A1_SM_A1 = 2 * WOB, A1_SM_A0 = A1_SM_A1 + 61440;
constexpr int A1_SM_XA = A1_SM_W0 + 2 * WOB, A1_SM_XB = A1_SM_XA + 2048;
constexpr int A1_SMEM = A1_SM_BAR + 512 + 7 * CST_EXTRA / 4;
static_assert(A1_SM_W3 >= A1_SM_KV + 144 * A1_KVP && A1_SM_W3 % 512 == 0 && A1_SM_A1 % 1024 == 0 && A1_SM_A0 <= A1_SM_KV && A1_SM_A0 + 61440 <= A1_SM_W3 && A1_SMEM <= 232448 && 11 * 4096 <= A1_STAGE, "layout");
__device__ __forceinline__ constexpr uint32_t wo_off(int h) { return h * WOB + (h < 3 ? A1_SM_W0 : h < 6 ? A1_SM_W3 - 3 * WOB : -6 * WOB); }
#define A1_FRED "red.relaxed.gpu.global.add.u32"
#define A1_FLD "ld.acquire.gpu.global.u32"
#define ST_SLEEP 20
#define ST_SLEEP0 300
#define WO_LATE bar_done
#define A1_P0 2
#define A1_PW (kb - 2)
#define A1_FSPIN SPIN_MAX
#define A1_FSLEEP 40
#define YT_LAYER 1
#define WOT 352
#define A1_WOAT 6

template <int L>
__device__ __forceinline__ void a1_mainloop(float (&acc)[120], uint32_t sbase, uint32_t bars, int wg, int tile) {
    constexpr int layer = L; (void)layer;
    const uint64_t da0 = L ? make_desc(sbase + wg * 8192, 8192, 1024, 1) : make_desc(sbase + wg * 8192, 16, 1024, 1), db0 = make_desc(sbase + 16384, 1024, 256, 3);
#pragma unroll 1
    for (int t = 0;; t++) {
        const int st = t % A1_NST;
        mbar_wait(bars + 8 * st, (t / A1_NST) & 1);
        if (t == A1_SKEW && wg == 0) mbar_wait(bars + 160, 0);
        TSTAMP3(1 + t);
        if (t == 0) CSA(0);
        wgmma_fence();
#pragma unroll
        for (int kk = 0; kk < 4; kk++) wgmma_n240<L, 1>(acc, da0 + (uint32_t)(st * (A1_STAGE / 16) + kk * (L ? 128 : 2)), db0 + (uint32_t)(st * (A1_STAGE / 16) + (kk >> 1) * (WQ_STAGE / 32) + (kk & 1) * 32), kk ? 1 : t);
        wgmma_commit();
        if (t == 9) break;
        if (t == A1_SKEW - 1 && wg == 0) wgmma_wait<0>(); else wgmma_wait<1>();
        if (t > 0 && (threadIdx.x & 127) == 0) {
            if (t != A1_SKEW || wg) mbar_arrive(bars + 8 * (A1_NST + (t - 1) % A1_NST));
            if (t == A1_SKEW - 1 && wg == 0) mbar_arrive(bars + 8 * (A1_NST + t % A1_NST));
        }
    }
}

template <bool MAP>
__global__ void __launch_bounds__(A1_THREADS, 1) a1_kernel(const __grid_constant__ Par in, const __grid_constant__ CUtensorMap tmX, const __grid_constant__ CUtensorMap tmR,
                                                           const __grid_constant__ CUtensorMap tmX1, const __grid_constant__ KgMaps tmW, const __grid_constant__ TileTab tab) {
#define layer in.layer
    const unsigned char* const wo = reinterpret_cast<const unsigned char*>(in.wop);
    float2* const rsum = reinterpret_cast<float2*>(in.sum);
    uint4* const of = in.of;
    extern __shared__ __align__(1024) unsigned char stg[];
    const uint32_t sbase = smem_u32(stg);
    const uint32_t bars = sbase + A1_SM_BAR;
    const uint32_t bar_stat = bars + 64, bar_kv = bars + 72, bar_rd = bars + 168;
    const uint32_t bar_wo = bars + 208, bar_done = bars + 216, bar_pv = bars + 224, bar_kvf = bars + 232, bar_f2 = bars + 248, bar_e2 = bars + 384, que = bars + 448;
    const int tid = threadIdx.x;
    CSK(0);
    const int w = __shfl_sync(~0u, tid >> 5, 0), wg = w >> 2;
    uint32_t smid;
    asm volatile("mov.u32 %0, %smid;" : "=r"(smid));
    const uint4 tv = tab.e[(MAP ? smid : blockIdx.x) + (tid & (smid >> 12))];
    const uint64_t pa = reinterpret_cast<const uint64_t*>(&in)[tid & (smid >> 12)], pb = reinterpret_cast<const uint64_t*>(&in)[6 + (tid & (smid >> 12))];
    const bool one = elect();
    uint32_t tz;
    const unsigned char* wq;
    auto entry = [&] { tz = __shfl_sync(~0u, tv.z, 0); wq = (const unsigned char*)(((uint64_t)__shfl_sync(~0u, tv.y, 0) << 32) | __shfl_sync(~0u, tv.x, 0)); };
    auto issue_w = [&](unsigned it) { bulk_load(sbase + (it % A1_NST) * A1_STAGE + 16384, wq + it * WQ_STAGE, WQ_STAGE, bars + 8 * (it % A1_NST)); };
    auto issue_x = [&](unsigned it, int kb) {
        asm volatile("cp.async.bulk.tensor.5d.shared::cluster.global.mbarrier::complete_tx::bytes [%0], [%1, {%3, %3, %3, %4, %5}], [%2];"
                     ::"r"(sbase + (it % A1_NST) * A1_STAGE), "l"(&tmX), "r"(bars + 8 * (it % A1_NST)), "r"(0), "r"(tz & 15), "r"(kb) : "memory");
    };
    auto first_x = [&] {
        issue_x(0, (tz >> 16) & 7); issue_x(1, ((tz >> 16) & 7) + 1);
    };
    auto expect = [&] {
#pragma unroll
        for (int i = 0; i < A1_NST; i++) mbar_expect_tx(bars + 8 * i, A1_STAGE);
    };
    if (w == 8) {
        if (one) {
            prefetch_tmap(&tmX); prefetch_tmap(&tmW.q);
#pragma unroll
            for (int i = 0; i < A1_NST; i++) mbar_init(bars + 8 * i, 1);
            asm volatile("fence.mbarrier_init.release.cluster;" ::: "memory");
        }
        __syncwarp();
        asm volatile("bar.arrive 0, 384;" ::: "memory");
        if (smid >> 12) __trap();
        entry();
        if ((tz & 0x80000010u) == 16) {
            if (one) {
                issue_w(0);
                asm volatile("griddepcontrol.wait;" ::: "memory");
                first_x();
                issue_w(1);
                expect();
                asm volatile("griddepcontrol.launch_dependents;" ::: "memory");
            }
#pragma unroll
            for (int kb = 2; kb < A1_NST; kb++) {
                __syncwarp();
                mbar_wait(bars + 8 * (kb - 2), 0);
                if (one) { issue_x(kb, ((tz >> 16) & 7) + kb); issue_w(kb); }
                CSK(6 + kb);
            }
        }
        __syncwarp();
        if (!(tz & 16) && blockIdx.x < 128) kgen_first(in, tmW, sbase + A1_SM_W0, bars - 24, one);
        __syncwarp();
    }
    if (w > 8) CSK(8);
    const bool gen = w != 8 && in.logA && blockIdx.x < 128;
    KgPar kp;
    const int w11 = w < 8 ? 2 * (w & 3) + (w >> 2) : w - 1;
    if (gen) kgen_load(in, reinterpret_cast<const bf16*>(pa), w11, kp);
    if (w > 8) CSK(9);
    if (w == 8) {
        const int tile = tz >> 24, mb = tz & 15, hg = (tz >> 8) & 7, kb0 = (tz >> 16) & 7;
        const unsigned l1 = (tz >> 4) & 1;
        if (__builtin_expect(!l1, 0)) {
            CSK(1);
            const uint32_t ep = ld_epoch();
            if (one) {
                kgen_side(in, sbase + A1_SM_W0, bars - 24);
                if (tile < 128) { first_x(); issue_x(2, kb0 + 2); expect(); }
                asm volatile("cp.async.bulk.wait_group 0;" ::: "memory");
            }
            __syncwarp();
            asm volatile("bar.arrive 10, 96;" ::: "memory");
            CSK(6);
            if (tile < 128) {
                await_all(96 + 32 * hg, ep * 15);
                if (one) { issue_w(0); issue_w(1); issue_w(2); }
            }
            CSK(7);
            asm volatile("bar.sync 3, 384;" ::: "memory");
            if (tile < 128 && one) {
                fence_async_smem();
                issue_x(3, kb0 + 3); issue_w(3);
                mbar_expect_tx(bars + 240, 20480);
                bulk_load(sbase + A1_SM_W0, in.x + (size_t)(mb * 128 + hg * 16) * DM, 20480, bars + 240);
            }
            __syncwarp();
            CSK(9);
        } else asm volatile("bar.sync 3, 64;" ::: "memory");
        if (tile < 128 && elect()) {
#pragma unroll 1
            for (unsigned kb = A1_NST; kb < 10; kb++) {
                mbar_wait(bars + 8 * (A1_NST + kb % A1_NST), ((kb / A1_NST) - 1) & 1);
                if (l1 && kb < 9) mbar_wait(bar_rd + 8 * (kb - A1_NST), 0);
                mbar_expect_tx(bars + 8 * (kb % A1_NST), A1_STAGE);
                issue_x(kb, kb < 5 ? kb + kb0 : kb - kb0); issue_w(kb);
                if (kb == (l1 ? A1_WOAT : 9)) {
                    if (!l1) { mbar_wait(bar_stat, 0); asm volatile("fence.proxy.async.global;" ::: "memory"); }
                    mbar_expect_tx(bar_wo, 8 * WOB);
                    bulk_load(sbase + A1_SM_W0, wo + hg * 8 * WOB, 2 * WOB, bar_wo);
                }
            }
            mbar_wait(bars + 8 * (A1_NST + 3), 1);
            bulk_load(sbase + A1_SM_W3, wo + (hg * 8 + 3) * WOB, 3 * WOB, bar_wo);
        }
        CSA(4); CSA_END;
        return;
    }
    {
        if (w < 8 && one) {
#pragma unroll 1
            for (uint32_t c = (w & 4 ? w & 2 ? 0x1111112'01111111ull : 0x1111111'01111184ull : w & 2 ? 0x3122222'01111111ull : 0x1111132'02220000ull) >> (32 * (w & 1)), b = bars + 56 * w; c; c >>= 4, b += 8)
                if (c & 15) mbar_init(b, c & 15);
            asm volatile("fence.mbarrier_init.release.cluster;" ::: "memory");
        }
        __syncwarp();
        asm volatile("bar.sync 0, 384;" ::: "memory");
        if (layer) {
            if (w == 9) asm volatile("bar.arrive 3, 64;" ::: "memory");
        } else {
            if (gen) { SPAN(0, 0); SPAN(0, 1); kgen_tables(in, reinterpret_cast<uint4*>(stg + 3 * A1_STAGE), w11, kp); }
            else if (w != 11 && w11 > 1) asm volatile("bar.arrive 9, 352;" ::: "memory");
            __syncwarp();
            if (w11 < 2) {
                asm volatile("bar.sync 10, 96;" ::: "memory");
                kgen_sums(in, sbase + A1_SM_W0, w11);
                __syncwarp();
                asm volatile("bar.arrive 9, 352;" ::: "memory");
                CSK(1);
            }
            if (w == 9) asm volatile("bar.sync 3, 384;" ::: "memory"); else asm volatile("bar.arrive 3, 384;" ::: "memory");
        }
    }
    tz = __shfl_sync(~0u, tv.z + (uint32_t)(pb >> 32), 0);
    const int tile = tz >> 24, mb = tz & 15, hg = (tz >> 8) & 7;
    float2* rst = reinterpret_cast<float2*>(stg + A1_SM_RS) + 8;
    if (wg == 2) {
        if (w == 11 && layer == 0) {
            asm volatile("bar.sync 9, 352;" ::: "memory");
            CSK(5);
            if (one) publish(64);
            __syncwarp();
            CSK(6);
        }
        if (tile >= 128) { sm_idle(layer); return; }
        if (w == 10) {
            if (one) { prefetch_tmap(&tmR); prefetch_tmap(&tmX1); }
            uint32_t ns;
            asm volatile("mov.u32 %0, %nsmid;" : "=r"(ns));
            if (MAP && ns != 132) __trap();
        }
        __syncwarp();
        if (w == 9) {
            if (layer && one) {
                mbar_expect_tx(bar_stat, 3840);
                bulk_load(sbase + A1_SM_XB, g_xb + tile * 240, 3840, bar_stat);
            }
            __syncwarp();
            uint4* pre = of + (mb * 8 + hg) * 1280 + (tid - 288);
#pragma unroll 1
            for (int k = 0; k < 5 + 5 * layer; k++) {
#pragma unroll
                for (int i = 0; i < 8; i++) asm volatile("st.global.v4.u32 [%0], {%1,%1,%1,%1};" ::"l"(pre + 32 * i), "r"(~0u) : "memory");
                pre += k < 5 ? 256 : XCP / 8;
                if (k == 4) {
                    CSA(2);
                    asm volatile("fence.acq_rel.gpu;" ::: "memory");
                    asm volatile("fence.proxy.async.global;" ::: "memory");
                    __syncwarp();
                    if (tid == 288) mbar_arrive(bar_done);
                    CSA(3);
                    pre = reinterpret_cast<uint4*>(g_yT) + tile * (5 * XCP / 8) + (tid - 288);
                }
            }
            if (layer == 0) {
                asm volatile("griddepcontrol.launch_dependents;" ::: "memory");
                await_all(64, ld_epoch() * gridDim.x);
                CSA(5);
                float4 a[2] = {};
#pragma unroll
                for (int k = 0; k < 10; k++)
#pragma unroll
                    for (int h = 0; h < 2; h++) {
                        const int c4 = min(tid - 288 + 32 * h, 59);
                        const float4 v = __ldcg(reinterpret_cast<const float4*>(g_csp + (k / 5) * 9600 + (k % 5) * 640 + hg * 80) + c4 + (c4 / 20) * 780);
                        a[h].x += v.x; a[h].y += v.y; a[h].z += v.z; a[h].w += v.w;
                    }
#pragma unroll
                for (int h = 0; h < 2; h++)
#pragma unroll
                    for (int k = 0; k < 4; k++) {
                        const float c = 0.5f * (k == 0 ? a[h].x : k == 1 ? a[h].y : k == 2 ? a[h].z : a[h].w), c1 = c - rbf(c), c2 = c1 - rbf(c1);
                        *reinterpret_cast<uint4*>(stg + A1_SM_XB + (4 * min(tid - 288 + 32 * h, 59) + k) * 16) = make_uint4(pack2(c, c1), pack2(c2, 0.f), 0u, 0u);
                    }
                fence_async_smem();
                __syncwarp();
                if (one) {
                    bulk_store(g_xb + tile * 240, sbase + A1_SM_XB, 3840);
                    asm volatile("cp.async.bulk.commit_group;" ::: "memory");
                    asm volatile("cp.async.bulk.wait_group.read 0;" ::: "memory");
                    mbar_arrive(bar_stat);
                }
                __syncwarp();
                CSA(1);
            }
            TSTAMP1T(9, 288);
        } else {
            const int j = tid - 320;
            const uint32_t tag = ld_epoch();
            if (tid == 352) sm_started(layer);
            const int ch = j & 7, kg = (j >> 3) & 3;
            const unsigned char* src = stg + (layer ? (j >> 5) * 8192 + (hg & 3) * 2048 : A1_SM_W0 + (j >> 2) * 1280);
            const int of0 = layer ? kg * 128 + ((ch ^ kg) << 4) : (j & 7) << 4, ofx = layer ? 576 : 64, ofy = layer ? 1024 : 128;
            float s[8], q[8], p0[8];
#pragma unroll
            for (int i = 0; i < 8; i++) { s[i] = 0.f; q[i] = 0.f; }
#pragma unroll 1
            for (int it = 0; it < 5; it++) {
                uint4 v[4];
                mbar_wait(layer ? bars + 8 * (it % A1_NST) : bars + 240, layer * it / A1_NST);
#pragma unroll
                for (int k = 0; k < 4; k++) v[k] = *reinterpret_cast<const uint4*>(src + (layer ? (it % A1_NST) * A1_STAGE : it * 256) + (k & 1 ? of0 ^ ofx : of0) + (k >> 1) * ofy);
                if (it == 0) {
                    const uint4 pv = *reinterpret_cast<const uint4*>(src + (layer ? ch << 4 : 0));
                    const uint32_t w[4] = {pv.x, pv.y, pv.z, pv.w};
#pragma unroll
                    for (int i = 0; i < 4; i++) { p0[2 * i] = __uint_as_float((layer ? w[i] : w[0]) << 16); p0[2 * i + 1] = __uint_as_float(layer ? w[i] & 0xffff0000u : w[0] << 16); }
                }
                asm volatile("" :: "r"(v[0].x), "r"(v[1].x), "r"(v[2].x), "r"(v[3].x), "f"(p0[0]) : "memory");
                __syncwarp();
                if ((tid & 31) == 0) mbar_arrive(bar_rd + 8 * it);
#pragma unroll
                for (int k = 0; k < 4; k++) {
                    const uint32_t w[4] = {v[k].x, v[k].y, v[k].z, v[k].w};
#pragma unroll
                    for (int i = 0; i < 4; i++) {
                        const float a = __uint_as_float(w[i] << 16) - p0[2 * i], b = __uint_as_float(w[i] & 0xffff0000u) - p0[2 * i + 1];
                        s[2 * i] += a; s[2 * i + 1] += b; q[2 * i] = fmaf(a, a, q[2 * i]); q[2 * i + 1] = fmaf(b, b, q[2 * i + 1]);
                    }
                }
            }
            float o[4];
            int row;
            if (layer == 0) {
                float s0 = ((s[0] + s[1]) + (s[2] + s[3])) + ((s[4] + s[5]) + (s[6] + s[7])), q0 = ((q[0] + q[1]) + (q[2] + q[3])) + ((q[4] + q[5]) + (q[6] + q[7]));
#pragma unroll
                for (int o = 1; o <= 2; o <<= 1) { s0 += __shfl_xor_sync(~0u, s0, o); q0 += __shfl_xor_sync(~0u, q0, o); }
                if ((j & 3) == 0) {
                    const float d = s0 * (1.0f / DM);
                    const uint32_t ms = pack2(p0[0] + d, sqrt_apx(rbf(rbf(fmaxf(fmaf(-d, d, q0 * (1.0f / DM)), 0.f)) + 1e-5f)));
                    asm volatile("st.global.cg.u64 [%0], %1;" ::"l"(g_rstat + mb * 128 + (j & 4) * 16 + hg * 8 + (j >> 3)), "l"(tagw(ms, tag)) : "memory");
                    g_piv[mb * 128 + hg * 16 + ((j >> 2) & 8) + (j & 4) + ((j >> 3) & 3)] = __ushort_as_bfloat16((unsigned short)ms);
                }
                ulonglong2 v;
#pragma unroll 1
                for (int it = 0; it < SPIN_MAX; it++) {
                    v = ld_tag2(reinterpret_cast<const ulonglong2*>(g_rstat + mb * 128) + j);
                    if (__all_sync(~0u, tag_ok(v, tag))) break;
                    __nanosleep(100);
                }
                o[0] = __uint_as_float((uint32_t)v.x << 16); o[1] = rcp_apx(__uint_as_float((uint32_t)v.x & 0xffff0000u));
                o[2] = __uint_as_float((uint32_t)v.y << 16); o[3] = rcp_apx(__uint_as_float((uint32_t)v.y & 0xffff0000u));
                row = 2 * j;
            } else {
#pragma unroll
                for (int i = 0; i < 4; i++) {
                    const bool up = kg & 2;
                    const float ss = __shfl_xor_sync(~0u, up ? s[i] : s[i + 4], 16), qq = __shfl_xor_sync(~0u, up ? q[i] : q[i + 4], 16);
                    s[i] = (up ? s[i + 4] : s[i]) + ss; q[i] = (up ? q[i + 4] : q[i]) + qq; p0[i] = up ? p0[i + 4] : p0[i];
                }
#pragma unroll
                for (int i = 0; i < 2; i++) {
                    const bool up = kg & 1;
                    const float ss = __shfl_xor_sync(~0u, up ? s[i] : s[i + 2], 8), qq = __shfl_xor_sync(~0u, up ? q[i] : q[i + 2], 8);
                    s[i] = (up ? s[i + 2] : s[i]) + ss; q[i] = (up ? q[i + 2] : q[i]) + qq; p0[i] = up ? p0[i + 2] : p0[i];
                }
                uint4* gp = g_halo + 86016 + mb * 512 + j;
                const float d0 = s[0] * (1.0f / 80.0f), d1 = s[1] * (1.0f / 80.0f);
                asm volatile("st.relaxed.gpu.global.v4.f32 [%0], {%1,%2,%3,%4};" ::"l"(gp + hg * 64), "f"(p0[0] + d0), "f"(fmaxf(fmaf(-d0, s[0], q[0]), 0.f)), "f"(p0[1] + d1), "f"(fmaxf(fmaf(-d1, s[1], q[1]), 0.f)) : "memory");
                __nanosleep(ST_SLEEP0);
                uint32_t pw[8][4], todo = 0xff;
#pragma unroll 1
                for (int it = 0; it < SPIN_MAX; it++) {
#pragma unroll
                    for (int k = 0; k < 8; k++)
                        if (todo >> k & 1) asm volatile("ld.relaxed.gpu.global.v4.u32 {%0,%1,%2,%3}, [%4];" : "=r"(pw[k][0]), "=r"(pw[k][1]), "=r"(pw[k][2]), "=r"(pw[k][3]) : "l"(gp + k * 64) : "memory");
#pragma unroll
                    for (int k = 0; k < 8; k++)
                        if (__all_sync(~0u, pw[k][0] != ~0u && pw[k][1] != ~0u && pw[k][2] != ~0u && pw[k][3] != ~0u)) todo &= ~(1u << k);
                    if (!todo) break;
                    __nanosleep(ST_SLEEP);
                }
#pragma unroll
                for (int r = 0; r < 2; r++) {
                    float mean = 0.f, m2 = 0.f;
#pragma unroll
                    for (int k = 0; k < 8; k++) mean += __uint_as_float(pw[k][2 * r]);
                    mean *= 0.125f;
#pragma unroll
                    for (int k = 0; k < 8; k++) {
                        const float dm = __uint_as_float(pw[k][2 * r]) - mean;
                        m2 += fmaf(80.0f * dm, dm, __uint_as_float(pw[k][2 * r + 1]));
                    }
                    o[2 * r] = rbf(mean);
                    o[2 * r + 1] = rcp_apx(rbf(sqrt_apx(rbf(rbf(m2 * (1.0f / DM)) + 1e-5f))));
                }
                row = (j >> 5) * 64 + (j & 7) * 8 + ((j >> 3) & 3) * 2;
                if (hg == 0) *reinterpret_cast<uint32_t*>(g_piv + SEQ + mb * 128 + 2 * (row & 60) + 4 * (row >> 6) + (row & 3)) = __byte_perm(__float_as_uint(o[0]), __float_as_uint(o[2]), 0x7632);
            }
#pragma unroll
            for (int r = 0; r < 2; r++)
                *reinterpret_cast<uint4*>(stg + A1_SM_XA + (row + r) * 16) = make_uint4(__byte_perm(__float_as_uint(-o[2 * r]), 0, 0x3232), __float_as_uint(-o[2 * r]) >> 16, 0u, 0u);
            *reinterpret_cast<float4*>(rst + row + (row >> 6) * 8) = make_float4(o[0], o[1], o[2], o[3]);
            fence_async_smem();
            TSTAMP1T(7, 320); CSA(1);
            if (tid == 320) DBGC(44);
            __syncwarp();
            if ((tid & 31) == 0) mbar_arrive(bar_stat);
        }
        CSA(4); CSA_END;
        if (tid == 320) DBGCAL(0);
        if (tid == WOT) {
            mbar_wait(WO_LATE, 0);
            mbar_wait(bar_done, 0);
            bulk_load(sbase, wo + (hg * 8 + 6) * WOB, 2 * WOB, bar_wo);
            bulk_load(sbase + A1_SM_W0 + 2 * WOB, wo + (hg * 8 + 2) * WOB, WOB, bar_wo);
        }
        __syncwarp();
#define FWA 11
#define FWB 10
        if (w == FWA || w == FWB) {
            const int cw = w == FWB;
            const uint32_t* fl = reinterpret_cast<const uint32_t*>(rsum + 2 * SEQ) + (((layer * 16 + mb) * 2 + cw) * 8 + (tid & 7)) * FSTR;
            const unsigned char* src = reinterpret_cast<const unsigned char*>(of) + mb * 163840 + cw * 10240 + (tid & 7) * 20480;
            const uint32_t sl = sbase + (cw ? A1_SM_A1 : A1_SM_A0);
            mbar_wait(cw ? bar_done : bar_kvf, 0);
            if ((tid & 31) == 0) {
                mbar_expect_tx(bar_f2 + 64 * cw + 64, 10240);
                tma_load_3d(sl + 51200, &tmR, layer ? 0 : hg * 80, layer ? hg * 80 : mb * 64, layer ? mb * 2 + cw : cw, bar_f2 + 64 * cw + 64);
            }
            __syncwarp();
            uint32_t pend = 0xffu & ~(1u << hg), v = 0;
            const uint32_t bo = wo_off((tid & 7) + ((tid & 7) < hg)) >> 4, lt = (1u << (tid & 31)) - 1;
#pragma unroll 1
            for (int it = 0; pend && it < 2 * SPIN_MAX; it++) {
                if (v != 4 && (pend >> (tid & 31) & 1)) asm volatile(A1_FLD " %0, [%1];" : "=r"(v) : "l"(fl) : "memory");
                uint32_t fr;
                asm volatile("{\n.reg .pred p;\nmbarrier.test_wait.parity.shared::cta.b64 p, [%1], 0;\nselp.b32 %0, 1, 0, p;\n}" : "=r"(fr) : "r"(bar_e2 + 16 * cw + (tid & 1) * 8) : "memory");
                fr = __ballot_sync(~0u, fr);
                uint32_t m = __ballot_sync(~0u, v == 4 || it >= A1_FSPIN) & pend;
                const int q = 8 - __popc(pend) + __popc(m & lt);
                m &= __ballot_sync(~0u, q < ((fr & 2) ? 8 : (fr & 1) ? 7 : 5));
                pend ^= m;
                if (m >> (tid & 31) & 1) DBGC(12 + cw * 8 + (tid & 7));
                if (!m) __nanosleep(A1_FSLEEP);
                else asm volatile("fence.proxy.async.global;" ::: "memory");
                if (m >> (tid & 31) & 1) {
                    bulk_load(q == 7 && !cw ? sbase + A1_SM_W0 : sl + (q < 6 ? q : q - 6) * 10240, src, 10240, bar_f2 + 64 * cw + 8 * q);
                    asm volatile("st.shared.u32 [%0], %1;" ::"r"(que + 32 * cw + 4 * q), "r"(bo) : "memory");
                    mbar_expect_tx(bar_f2 + 64 * cw + 8 * q, 10240);
                    DBGC(44 + cw * 8 + q);
                }
                __syncwarp();
            }
        }
    } else if (tile < 128) {
        SPAN(1 + 4 * layer, 0);
        constexpr int on = 1;
        float acc[120];
        const int lane = tid & 31, warp = w & 7, g = lane >> 2, t = lane & 3;
        if (on) {
            SPAN(1 + 4 * layer, 1);
            TSTAMP1(0);
            if (threadIdx.x == 0) { GSTAMP(g_tim1, 15); }
            TSTAMP3(0);
            if (tid == 0) TSTAMP2(0);
            TSTAMP4(0);
            if (tid == 0) DBGC(60);
            if (layer == 0) a1_mainloop<0>(acc, sbase, bars, wg, tile); else a1_mainloop<1>(acc, sbase, bars, wg, tile);
            uint32_t ok;
            asm volatile("{\n.reg .pred p;\nmbarrier.test_wait.parity.shared::cta.b64 p, [%1], 0;\nselp.b32 %0, 1, 0, p;\n}" : "=r"(ok) : "r"(bar_stat) : "memory");
            if (tid == 128 && !ok) mbar_arrive(bars + 160);
            __syncwarp();
            mbar_wait(bar_stat, 0);
            wgmma_fence();
            wgmma_n240<0, 0>(acc, make_desc(sbase + A1_SM_XA + wg * 1024, 0, 128, 0), make_desc(sbase + A1_SM_XB, 0, 128, 0), 1);
            wgmma_commit();
            if (tid == 128 && ok) mbar_arrive(bars + 160);
            mbar_wait(bars + 8 * (A1_NST + 3), 1);
        }
        const float2* rw = rst + 16 * warp + 8 * wg;
        const float rb0 = rw[g + 8].y, ra = rw[g].y * 0.22360679774997896f, rb = rb0 * 0.22360679774997896f;
        wgmma_wait<0>();
        if ((tid & 127) == 0) mbar_arrive(bar_done);
        TSTAMP1(2); CSA(1);
        TSTAMP1T(13, 224);
        if ((tid & 127) == 0) DBGC(62 - wg);
        uint32_t f[2][30];
#pragma unroll
        for (int j = 10; j < 30; j++) f[1][j] = pack2(acc[4 * j + 2], acc[4 * j + 3]);
        if ((warp & 3) == 3) {
            uint4* hout = g_halo + (((layer * 16 + mb) * 8 + hg) * 2 + wg) * 168;
#pragma unroll
            for (int j = 0; j < 20; j += 4)
                asm volatile("st.relaxed.gpu.global.v4.u32 [%0], {%1,%2,%3,%4};" ::"l"(hout + 8 * j + lane), "r"(f[1][10 + j]), "r"(f[1][11 + j]), "r"(f[1][12 + j]), "r"(f[1][13 + j]) : "memory");
            if (t == 0) asm volatile("st.relaxed.gpu.global.f32 [%0], %1;" ::"l"(reinterpret_cast<float*>(hout + 160) + g), "f"(rb0) : "memory");
        }
        TSTAMP1T(12, 224);
        const uint32_t kvw = sbase + A1_SM_KV + (16 * warp + 8 * wg) * A1_KVP;
        const uint32_t mrow = kvw + (lane & 7) * A1_KVP + (lane >> 3) * 16;
#pragma unroll
        for (int j = 0; j < 20; j += 4) stsm_x4(mrow + 16 * A1_KVP + 16 * j, f[1][10 + j], f[1][11 + j], f[1][12 + j], f[1][13 + j]);
        __syncwarp();
        if (lane == 0 && (warp & 3) != 3) mbar_arrive(bar_kv + 8 * (warp + 1));
#pragma unroll
        for (int j = 0; j < 30; j++) f[0][j] = pack2(acc[4 * j], acc[4 * j + 1]);
        stsm_x4(mrow + 8 * A1_KVP + 160, f[0][20], f[0][21], f[0][22], f[0][23]);
        stsm_x4(mrow + 8 * A1_KVP + 224, f[0][24], f[0][25], f[0][26], f[0][27]);
        asm volatile("stmatrix.sync.aligned.m8n8.x2.shared.b16 [%0], {%1,%2};" ::"r"(mrow + 8 * A1_KVP + 288), "r"(f[0][28]), "r"(f[0][29]) : "memory");
#pragma unroll
        for (int j = 0; j < 10; j++) f[1][j] = pack2(acc[4 * j + 2], acc[4 * j + 3]);
        __syncwarp();
        uint32_t vb[10][2], vp[12], kp[12];
#pragma unroll
        for (int j = 0; j < 10; j += 2) ldsm_x4_t(&vb[j][0], kvw + (8 + (lane & 15)) * A1_KVP + 160 + (lane >> 4) * 16 + 16 * j);
        const bool up0 = 2 * t > g, up1 = 2 * t + 1 > g, edge = (mb | (warp & 3)) == 0;
        float rk[4];
        auto above = [&]() {
            mbar_wait(bar_kv + 8 * warp, 0);
#pragma unroll
            for (int j = 0; j < 12; j += 4) ldsm_x4(&kp[j], mrow + 16 * j);
            rk[0] = rw[2 * t - (up0 ? 8 : 0)].y; rk[1] = rw[2 * t + 1 - (up1 ? 8 : 0)].y;
#pragma unroll
            for (int j = 0; j < 12; j += 4) ldsm_x4_t(&vp[j], mrow + 160 + 16 * j - (j == 8 ? (lane & 16) * 2 : 0));
            __syncwarp();
            if (lane == 0) mbar_arrive(bar_kvf);
        };
        auto halo = [&]() {
            if (lane == 0) mbar_arrive(bar_kvf);
            const uint4* hin = g_halo + (((layer * 16 + mb - 1) * 8 + hg) * 2 + wg) * 168;
            uint32_t hv[22] = {};
            rk[0] = rw[2 * t].y; rk[1] = rw[2 * t + 1].y;
            if (mb > 0) {
#pragma unroll 1
                for (int it = 0; it < SPIN_MAX; it++) {
#pragma unroll
                    for (int k = 0; k < 20; k += 4)
                        asm volatile("ld.relaxed.gpu.global.v4.u32 {%0,%1,%2,%3}, [%4];" : "=r"(hv[k]), "=r"(hv[k + 1]), "=r"(hv[k + 2]), "=r"(hv[k + 3]) : "l"(hin + 8 * k + lane) : "memory");
                    asm volatile("ld.relaxed.gpu.global.v2.u32 {%0,%1}, [%2];" : "=r"(hv[20]), "=r"(hv[21]) : "l"(reinterpret_cast<const uint2*>(hin + 160) + t) : "memory");
                    uint32_t m = max(hv[20], hv[21]);
#pragma unroll
                    for (int k = 0; k < 20; k += 2) m = __vimax3_u32(m, hv[k], hv[k + 1]);
                    if (!__any_sync(~0u, m == ~0u)) break;
                }
            }
            if (lane == 0) DBGC(52 - 16 * wg);
#pragma unroll
            for (int j = 0; j < 10; j++) {
                kp[j] = hv[j];
                asm volatile("movmatrix.sync.aligned.m8n8.trans.b16 %0, %1;" : "=r"(vp[j]) : "r"(hv[10 + j]));
            }
            if (up0) rk[0] = __uint_as_float(hv[20]);
            if (up1) rk[1] = __uint_as_float(hv[21]);
        };
        rk[2] = rw[2 * t + (up0 ? 0 : 8)].y; rk[3] = rw[2 * t + 1 + (up1 ? 0 : 8)].y;
        uint32_t qs[4][2];
#pragma unroll
        for (int h = 0; h < 4; h++) {
            qs[h][0] = (t >> 1) == (h & 1) ? f[0][5 * (h >> 1) + 2] : 0u; qs[h][1] = (t >> 1) == (h & 1) ? f[1][5 * (h >> 1) + 2] : 0u;
            asm volatile("" : "+r"(qs[h][0]), "+r"(qs[h][1]));
        }
#pragma unroll
        for (int j = 0; j < 10; j++) asm volatile("" : "+r"(f[0][j]), "+r"(f[1][j]), "+r"(f[0][10 + j]));
        if (warp & 3) above(); else if (wg) halo();
        TSTAMP1T(10, 64); CSA(2);
        if (warp && !wg) mbar_wait(bars + 416 + 8 * warp, 0);
        CSA(3);
        float sc[4][3][4];
#pragma unroll
        for (int h = 0; h < 4; h++) {
            const int jb = 5 * (h >> 1) + 3 * (h & 1), js = 5 * (h >> 1) + 2;
#pragma unroll
            for (int nt = 1; nt < 3; nt++) {
#pragma unroll
                for (int e = 0; e < 4; e++) sc[h][nt][e] = 0.f;
                mma_bf16(sc[h][nt], f[0][jb], f[1][jb], f[0][jb + 1], f[1][jb + 1], f[nt - 1][10 + jb], f[nt - 1][11 + jb]);
                mma_bf16_k8(sc[h][nt], qs[h][0], qs[h][1], f[nt - 1][10 + js]);
            }
        }
        if (warp == 0) halo();
        TSTAMP1(8); CSA(4);
#pragma unroll
        for (int h = 0; h < 4; h++) {
            const int jb = 5 * (h >> 1) + 3 * (h & 1), js = 5 * (h >> 1) + 2;
#pragma unroll
            for (int e = 0; e < 4; e++) sc[h][0][e] = 0.f;
            mma_bf16(sc[h][0], f[0][jb], f[1][jb], f[0][jb + 1], f[1][jb + 1], kp[jb], kp[jb + 1]);
            mma_bf16_k8(sc[h][0], qs[h][0], qs[h][1], kp[js]);
        }
        TSTAMP1T(3, 64);
        float p[4][4], sum[4][2];
        uint32_t lg[4][2], mx[4];
        const float rl[4] = {rk[0] * ra, rk[1] * ra, rk[2] * rb, rk[3] * rb};
        auto max2 = [](uint32_t a, uint32_t b) { uint32_t r; asm("max.bf16x2 %0, %1, %2;" : "=r"(r) : "r"(a), "r"(b)); return r; };
#pragma unroll
        for (int h = 0; h < 4; h++) {
            lg[h][0] = pack2((up0 ? sc[h][0][0] : sc[h][1][0]) * rl[0], (up0 ? sc[h][1][2] : sc[h][2][2]) * rl[2]);
            lg[h][1] = pack2((up1 ? sc[h][0][1] : sc[h][1][1]) * rl[1], (up1 ? sc[h][1][3] : sc[h][2][3]) * rl[3]);
            if (edge) {
                if (up0) lg[h][0] = __byte_perm(lg[h][0], 0xce6eu, 0x3254);
                if (up1) lg[h][1] = __byte_perm(lg[h][1], 0xce6eu, 0x3254);
            }
            mx[h] = max2(lg[h][0], lg[h][1]);
        }
#pragma unroll
        for (int o = 1; o <= 2; o <<= 1)
#pragma unroll
            for (int h = 0; h < 4; h++) mx[h] = max2(mx[h], __shfl_xor_sync(~0u, mx[h], o));
#pragma unroll
        for (int h = 0; h < 4; h++)
#pragma unroll
            for (int r = 0; r < 2; r++) {
                const float m = __uint_as_float(r ? mx[h] & 0xffff0000u : mx[h] << 16);
#pragma unroll
                for (int e = 0; e < 2; e++)
                    asm("ex2.approx.ftz.f32 %0, %1;" : "=f"(p[h][2 * r + e]) : "f"((__uint_as_float(r ? lg[h][e] & 0xffff0000u : lg[h][e] << 16) - m) * 1.4426950408889634f));
                sum[h][r] = p[h][2 * r] + p[h][2 * r + 1];
            }
#pragma unroll
        for (int o = 1; o <= 2; o <<= 1)
#pragma unroll
            for (int h = 0; h < 4; h++)
#pragma unroll
                for (int r = 0; r < 2; r++) sum[h][r] += __shfl_xor_sync(~0u, sum[h][r], o);
        TSTAMP1T(5, 64); CSA(5);
        const uint32_t mu = (up0 ? 0xffffu : 0u) | (up1 ? 0xffff0000u : 0u);
        uint32_t ob[10][2];
#pragma unroll
        for (int P = 0; P < 2; P++) {
            float os[2][4];
#pragma unroll
            for (int e = 0; e < 2; e++) {
                const int h = 2 * P + e;
                const float i0 = rcp_apx(sum[h][0]), i1 = rcp_apx(sum[h][1]);
                const uint32_t w0 = pack2(p[h][0] * rk[0] * i0, p[h][1] * rk[1] * i0), w1 = pack2(p[h][2] * rk[2] * i1, p[h][3] * rk[3] * i1);
#pragma unroll
                for (int dt = 0; dt < 3; dt++) {
                    const int j = 5 * P + (dt < 2 ? 3 * e + dt : 2);
                    float o[4] = {0.f, 0.f, 0.f, 0.f};
                    mma_bf16(o, w0 & ~mu, w1 & mu, 0u, w1 & ~mu, vb[j][0], vb[j][1]);
                    mma_bf16_k8(o, w0 & mu, 0u, vp[j]);
                    if (dt < 2) { ob[j][0] = pack2(o[0], o[1]); ob[j][1] = pack2(o[2], o[3]); }
                    else { os[e][0] = o[0]; os[e][1] = o[1]; os[e][2] = o[2]; os[e][3] = o[3]; }
                }
            }
#pragma unroll
            for (int k = 0; k < 4; k++) os[0][k] = t < 2 ? os[0][k] : os[1][k];
            ob[5 * P + 2][0] = pack2(os[0][0], os[0][1]); ob[5 * P + 2][1] = pack2(os[0][2], os[0][3]);
        }
        const uint32_t sl = sbase + (wg ? A1_SM_A1 : A1_SM_A0);
        const uint32_t o0 = (warp & 3) * 2048 + g * 64 + ((t ^ (g >> 1)) << 4), o1 = 8192 + (warp & 3) * 512 + g * 32 + ((t ^ ((g >> 2) << 1)) << 3);
        CSA(15);
        mbar_wait(bar_done, 0);
        if (wg == 0) mbar_wait(bar_kvf, 0);
#pragma unroll
        for (int h = 0; h < 2; h++) {
            asm volatile("st.shared.v4.u32 [%0], {%1,%2,%3,%4};" ::"r"(sl + o0 + h * 1024), "r"(ob[0][h]), "r"(ob[1][h]), "r"(ob[2][h]), "r"(ob[3][h]) : "memory");
            asm volatile("st.shared.v4.u32 [%0], {%1,%2,%3,%4};" ::"r"(sl + o0 + h * 1024 + 512), "r"(ob[4][h]), "r"(ob[5][h]), "r"(ob[6][h]), "r"(ob[7][h]) : "memory");
            asm volatile("st.shared.v2.u32 [%0], {%1,%2};" ::"r"(sl + o1 + h * 256), "r"(ob[8][h]), "r"(ob[9][h]) : "memory");
        }
        if (wg && lane == 0) mbar_arrive(bars + 384 + 8 * warp);
        fence_async_smem();
        __syncwarp();
        TSTAMP1T(4, 64); CSA(6);
        TSTAMP1(1);
        TSTAMP2(1);
        const unsigned char* ot = reinterpret_cast<const unsigned char*>(of) + mb * 163840 + wg * 10240;
        if (lane == 0) {
            asm volatile("cp.async.bulk.global.shared::cta.bulk_group [%0], [%1], 2048;" ::"l"(ot + hg * 20480 + (warp & 3) * 2048), "r"(sl + (warp & 3) * 2048) : "memory");
            asm volatile("cp.async.bulk.global.shared::cta.bulk_group [%0], [%1], 512;" ::"l"(ot + hg * 20480 + 8192 + (warp & 3) * 512), "r"(sl + 8192 + (warp & 3) * 512) : "memory");
            asm volatile("cp.async.bulk.commit_group;" ::: "memory");
            if (wg == 0) mbar_arrive(bar_pv);
            asm volatile("cp.async.bulk.wait_group 0;" ::: "memory");
            asm volatile(A1_FRED " [%0], 1;" ::"l"(reinterpret_cast<uint32_t*>(rsum + 2 * SEQ) + (((layer * 16 + mb) * 2 + wg) * 8 + hg) * FSTR) : "memory");
            DBGC(4 + warp);
        }
        TSTAMP4(11); CSA(7);
        float ac2[40];
        const uint64_t db0 = make_desc(sbase, 1024, 256, 3), db1 = make_desc(sbase + 10240, 512, 256, 3), da0 = make_desc(sl, 16, 1024, 2), da1 = make_desc(sl + 8192, 16, 256, 3);
        const uint32_t o7 = wg ? 640 : (A1_SM_W0 - A1_SM_A0) >> 4;
        const uint32_t trow = ((lane & 7) + 8 * (lane >> 4)) * 128 + (((2 * (warp & 3) + ((lane >> 3) & 1)) ^ (lane & 7)) << 4);
        uint32_t xr[10][2];
        mbar_wait(bar_f2 + 64 * wg + 64, 0);
        if (layer == 0) {
#pragma unroll
            for (int j = 0; j < 10; j += 2) ldsm_x4(&xr[j][0], sl + 51200 + (16 * (warp & 3) + (lane & 15)) * 160 + (lane >> 4) * 16 + 16 * j);
        } else {
#pragma unroll
            for (int j = 0; j < 10; j += 2) ldsm_x4_t(&xr[j][0], sl + 51200 + trow + 1024 * j);
        }
        const uint32_t ri = __shfl_sync(~0u, layer * SEQ + (wg * 2 + ((g >> 1) & 1)) * 512 + (mb * 16 + 4 * (warp & 3) + (g >> 2)) * 2 + (g & 1), lane);
        mbar_wait(bar_wo, 0);
        if (wg) mbar_wait(bar_pv, 0);
        if (wg) asm volatile("bar.sync 2, 128;" ::: "memory"); else asm volatile("bar.sync 1, 128;" ::: "memory");
        TSTAMP2(2); CSA(8);
#pragma unroll
        for (int q = 0; q < 8; q++) {
            uint32_t bo = wo_off(0) >> 4;
            if (q) {
                mbar_wait(bar_f2 + 64 * wg + 8 * q, 0);
                asm volatile("ld.shared.u32 %0, [%1];" : "=r"(bo) : "r"(que + 32 * wg + 4 * q) : "memory");
                bo = __shfl_sync(~0u, bo, 0);
                TSTAMP4(q);
                if (q % 3 == 1) CSA(9 + q / 3);
                if (q == 1 && (tid & 127) == 0) DBGC(29 + 8 * wg);
            }
            wgmma_fence();
#pragma unroll
            for (int j = 0; j < 5; j++) wgmma_n80(ac2, (j < 4 ? da0 : da1) + (q == 7 ? o7 : 0u) + (uint64_t)((q < 6 ? q * 640 : 0) + (j & 2) * 16 + (j & 1) * 2), (j < 4 ? db0 : db1) + bo + (uint64_t)((j & 2) * 160 + (j & 1) * 32), j || q);
            wgmma_commit();
            if (q == 0) {
                wgmma_wait<0>();
                if ((tid & 127) == 0) { mbar_arrive(bar_e2 + 16 * wg); mbar_arrive(bar_e2 + 8); }
            }
            if (q == 2 && wg) {
                wgmma_wait<1>();
                if (tid == 128) mbar_arrive(bar_e2 + 24);
            }
        }
        if ((tid & 127) == 0) DBGC(28 + wg * 8 + 7);
        TSTAMP2(3);
        wgmma_wait<0>();
        TSTAMP2(4); CSA(12);
        if (__any_sync(~0u, ac2[0] != ac2[0] || ac2[2] != ac2[2])) {
#pragma unroll
            for (int i = 0; i < 40; i++) ac2[i] = 0.f;
            uint32_t a[20], an[20];
            auto lda = [&](uint32_t (&r)[20], int h) {
#pragma unroll
                for (int u = 0; u < 4; u++)
                    asm volatile("ld.relaxed.gpu.global.v4.u32 {%0,%1,%2,%3}, [%4];" : "=r"(r[4 * u]), "=r"(r[4 * u + 1]), "=r"(r[4 * u + 2]), "=r"(r[4 * u + 3]) : "l"(ot + h * 20480 + o0 + u * 512) : "memory");
#pragma unroll
                for (int u = 0; u < 2; u++)
                    asm volatile("ld.relaxed.gpu.global.v2.u32 {%0,%1}, [%2];" : "=r"(r[16 + 2 * u]), "=r"(r[17 + 2 * u]) : "l"(ot + h * 20480 + o1 + u * 256) : "memory");
            };
            lda(an, 0);
#pragma unroll 5
            for (int k = lane; k < WOB / 16; k += 32)
                reinterpret_cast<uint4*>(stg + (sl - sbase))[k] = __ldcg(reinterpret_cast<const uint4*>(wo + hg * 8 * WOB) + k);
            __syncwarp();
#pragma unroll 1
            for (int h = 0; h < 8; h++) {
#pragma unroll 1
                for (int it = 0; it < SPIN_MAX; it++) {
                    uint32_t m = 0;
#pragma unroll
                    for (int k = 0; k < 20; k += 2) m = __vimax3_u32(m, an[k], an[k + 1]);
                    if (!__any_sync(~0u, m == ~0u)) break;
                    lda(an, h);
                }
#pragma unroll
                for (int k = 0; k < 20; k++) a[k] = an[k];
                lda(an, min(h + 1, 7));
                const uint32_t bp = h == hg ? sl : sbase + wo_off(h + (h < hg));
                const int r0 = 8 * ((lane & 7) >> 1) + 2 * (lane >> 3) + (lane & 1), r2 = 4 * ((lane & 7) >> 1) + 2 * ((lane >> 3) & 1) + (lane & 1);
#pragma unroll
                for (int n = 0; n < 10; n++) {
                    uint32_t b[12];
                    ldsm_x4_t(b, bp + (n >> 1) * 1024 + r0 * 32 + (((n ^ (r0 >> 2)) & 1) << 4));
                    ldsm_x4_t(b + 4, bp + 5120 + (n >> 1) * 1024 + r0 * 32 + (((n ^ (r0 >> 2)) & 1) << 4));
                    ldsm_x4_t(b + 8, bp + 10240 + (n >> 1) * 512 + r2 * 32 + (((n ^ (r2 >> 2)) & 1) << 4));
                    mma_bf16(ac2 + 4 * n, a[0], a[8], a[1], a[9], b[0], b[1]); mma_bf16(ac2 + 4 * n, a[2], a[10], a[3], a[11], b[2], b[3]);
                    mma_bf16(ac2 + 4 * n, a[4], a[12], a[5], a[13], b[4], b[5]); mma_bf16(ac2 + 4 * n, a[6], a[14], a[7], a[15], b[6], b[7]);
                    mma_bf16(ac2 + 4 * n, a[16], a[18], a[17], a[19], b[8], b[9]);
                }
            }
        }
#pragma unroll
        for (int j = 0; j < 10; j++)
#pragma unroll
            for (int hh = 0; hh < 2; hh++) {
                const uint32_t a = pack2(ac2[4 * j + 2 * hh], ac2[4 * j + 2 * hh + 1]);
                const __nv_bfloat162 r = __hadd2_rn(*reinterpret_cast<const __nv_bfloat162*>(&xr[j][hh]), *reinterpret_cast<const __nv_bfloat162*>(&a));
                xr[j][hh] = *reinterpret_cast<const uint32_t*>(&r);
            }
        const uint32_t so = sl + 30720;
#pragma unroll
        for (int j = 0; j < 10; j += 2) stsm_x4_t(so + trow + 1024 * j, xr[j][0], xr[j][1], xr[j + 1][0], xr[j + 1][1]);
        if (wg) asm volatile("bar.sync 2, 128;" ::: "memory"); else asm volatile("bar.sync 1, 128;" ::: "memory");
        TSTAMP2(5); CSA(13);
        if ((tid & 127) == 0) {
            fence_async_smem();
            asm volatile("cp.async.bulk.tensor.2d.global.shared::cta.bulk_group [%0, {%1, %2}], [%3];" ::"l"(&tmX1), "r"(mb * 128 + 64 * wg), "r"(hg * 80), "r"(so) : "memory");
            asm volatile("cp.async.bulk.commit_group;" ::: "memory");
        }
        __syncwarp();
        const float p0 = *(volatile const float*)&rw[g].x, p1 = *(volatile const float*)&rw[g + 8].x;
        float s[3][4] = {};
        const uint32_t pp[2] = {__byte_perm(__float_as_uint(p0), 0, 0x3232), __byte_perm(__float_as_uint(p1), 0, 0x3232)};
#pragma unroll
        for (int j = 0; j < 10; j += 2) {
            const uint32_t d0 = sub2(xr[j][0], pp[0]), d1 = sub2(xr[j][1], pp[1]), d2 = sub2(xr[j + 1][0], pp[0]), d3 = sub2(xr[j + 1][1], pp[1]);
            mma_bf16(s[0], xr[j][0], xr[j][1], xr[j + 1][0], xr[j + 1][1], 0x3f803f80u, 0x3f803f80u);
            mma_bf16(s[1], d0, d1, d2, d3, d0, d2);
            mma_bf16(s[2], d0, d1, d2, d3, d1, d3);
        }
        if (t == (g >> 1)) {
            float2* rp = rsum + ri;
            asm volatile("red.relaxed.gpu.global.add.v2.f32 [%0], {%1, %2};" ::"l"(rp), "f"(fmaf(-80.f, p0, s[0][0])), "f"((g & 1) ? s[1][1] : s[1][0]) : "memory");
            asm volatile("red.relaxed.gpu.global.add.v2.f32 [%0], {%1, %2};" ::"l"(rp + 4), "f"(fmaf(-80.f, p1, s[0][2])), "f"((g & 1) ? s[2][3] : s[2][2]) : "memory");
        }
        asm volatile("cp.async.bulk.wait_group.read 0;" ::: "memory");
        TSTAMP2(6); CSA(14); CSA_END;
        if (tid == 0) DBGC(63);
        if (tid == 128) DBGC(28);
        if (tid == 0) DBGCAL(2);
        GSTAMP(g_tim1, 14);
        SPAN(1 + 4 * layer, 3);
    }
#undef layer
}

static int h_nsm;
static void* h_sym[11];
static TileTab h_tab[2];
static CUtensorMap h_tmX0, h_tmX1, h_tmR0, h_tmR1, h_tmX1st, h_tmOut;
static KgMaps h_tmW;
typedef CUresult (*PFN_encodeTiled)(CUtensorMap*, CUtensorMapDataType, cuuint32_t, void*, const cuuint64_t*, const cuuint64_t*,
                                    const cuuint32_t*, const cuuint32_t*, CUtensorMapInterleave, CUtensorMapSwizzle,
                                    CUtensorMapL2promotion, CUtensorMapFloatOOBfill);
static void make_tmap(CUtensorMap* tm, const void* ptr, uint64_t cols, uint64_t rows, uint32_t bc, uint32_t br, CUtensorMapSwizzle sw, uint64_t pitch = 0, uint64_t hi = 0, uint32_t bh = 2) {
    static PFN_encodeTiled fn = nullptr;
    if (!fn) {
        void* p = nullptr; cudaDriverEntryPointQueryResult qr;
        cudaGetDriverEntryPoint("cuTensorMapEncodeTiled", &p, cudaEnableDefault, &qr);
        fn = (PFN_encodeTiled)p;
    }
    if (br == 0) {
        cuuint64_t dims[5] = {16, 2, rows / 8, 4, cols / 16}; cuuint64_t strides[4] = {cols * 2, cols * 16, cols * 4, 32};
        cuuint32_t box[5] = {16, 2, bc, 4, 5}; cuuint32_t es[5] = {1, 1, 1, 1, 1};
        fn(tm, CU_TENSOR_MAP_DATA_TYPE_BFLOAT16, 5, const_cast<void*>(ptr), dims, strides, box, es, CU_TENSOR_MAP_INTERLEAVE_NONE, sw,
           CU_TENSOR_MAP_L2_PROMOTION_L2_128B, CU_TENSOR_MAP_FLOAT_OOB_FILL_NONE);
        return;
    }
    if (hi == 16) {
        cuuint64_t dims[4] = {16, 32, 120, 20}; cuuint64_t strides[3] = {3840, 32, 32 * 3840};
        cuuint32_t box[4] = {16, 32, 5, 2}; cuuint32_t es[4] = {1, 1, 1, 1};
        fn(tm, CU_TENSOR_MAP_DATA_TYPE_BFLOAT16, 4, const_cast<void*>(ptr), dims, strides, box, es, CU_TENSOR_MAP_INTERLEAVE_NONE, sw,
           CU_TENSOR_MAP_L2_PROMOTION_L2_128B, CU_TENSOR_MAP_FLOAT_OOB_FILL_NONE);
        return;
    }
    if (bh == 0) {
        cuuint64_t dims[5] = {64, 64, 2, 16, 10}; cuuint64_t strides[4] = {pitch * 2, hi * 2, cols * 2, rows * 2};
        cuuint32_t box[5] = {64, 64, 2, 1, 1}; cuuint32_t es[5] = {1, 1, 1, 1, 1};
        fn(tm, CU_TENSOR_MAP_DATA_TYPE_BFLOAT16, 5, const_cast<void*>(ptr), dims, strides, box, es, CU_TENSOR_MAP_INTERLEAVE_NONE, sw,
           CU_TENSOR_MAP_L2_PROMOTION_L2_128B, CU_TENSOR_MAP_FLOAT_OOB_FILL_NONE);
        return;
    }
    if (hi) {
        cuuint64_t dims[3] = {cols, rows, hi == 64 ? 32u : 2u}; cuuint64_t strides[2] = {pitch * 2, hi * 2};
        cuuint32_t box[3] = {bc, br, bh}; cuuint32_t es[3] = {1, 1, 1};
        fn(tm, CU_TENSOR_MAP_DATA_TYPE_BFLOAT16, 3, const_cast<void*>(ptr), dims, strides, box, es, CU_TENSOR_MAP_INTERLEAVE_NONE, sw,
           CU_TENSOR_MAP_L2_PROMOTION_L2_128B, CU_TENSOR_MAP_FLOAT_OOB_FILL_NONE);
        return;
    }
    cuuint64_t dims[2] = {cols, rows}; cuuint64_t strides[1] = {(pitch ? pitch : cols) * 2};
    cuuint32_t box[2] = {bc, br}; cuuint32_t es[2] = {1, 1};
    fn(tm, CU_TENSOR_MAP_DATA_TYPE_BFLOAT16, 2, const_cast<void*>(ptr), dims, strides, box, es, CU_TENSOR_MAP_INTERLEAVE_NONE, sw,
       CU_TENSOR_MAP_L2_PROMOTION_L2_128B, CU_TENSOR_MAP_FLOAT_OOB_FILL_NONE);
}
template <typename... Args>
static void launch_pdl(void (*kern)(Args...), int grid, int block, int smem, Args... args) {
    cudaLaunchConfig_t cfg = {};
    cfg.gridDim = dim3(grid); cfg.blockDim = dim3(block); cfg.dynamicSmemBytes = smem; cfg.stream = cudaStreamPerThread;
    cudaLaunchAttribute at[1];
    at[0].id = cudaLaunchAttributeProgrammaticStreamSerialization; at[0].val.programmaticStreamSerializationAllowed = 1;
    cfg.attrs = at; cfg.numAttrs = 1;
    cudaLaunchKernelEx(&cfg, kern, args...);
}
static void launch_stage(int k, void* const* d_in, void* d_out) {
    const Par par = {k > 1 ? nullptr : (const bf16*)d_in[4], (const bf16*)d_in[5], (const bf16*)d_in[6], (const bf16*)d_in[7], (const bf16*)d_in[8], (const bf16*)d_in[9], k > 1, 0, (const bf16*)d_in[0],
                     (uint4*)h_sym[4], (uint4*)h_sym[2], (uint4*)h_sym[6], (uint4*)h_sym[3], (uint4*)h_sym[0], (float*)h_sym[5], (uint4*)h_sym[1], (const bf16*)d_in[1], (const bf16*)d_in[2]};
    auto a1 = h_nsm == 132 ? a1_kernel<true> : a1_kernel<false>;
    switch (k) {
        case 1: a1<<<h_nsm, A1_THREADS, A1_SMEM, cudaStreamPerThread>>>(par, h_tmX0, h_tmR0, h_tmX1st, h_tmW, h_tab[0]); break;
        case 3: launch_pdl(conv_kernel, DM / CV_CPB, CV_THREADS, CV_SMEM, 0, (const uint4*)h_sym[7], (const float4*)h_sym[4], (const bf16*)h_sym[8], (bf16*)h_sym[9], (const uint4*)h_sym[0], h_tmOut); break;
        case 5: launch_pdl(a1, h_nsm, A1_THREADS, A1_SMEM, par, h_tmX1, h_tmR1, h_tmX1st, h_tmW, h_tab[1]); break;
        case 7: launch_pdl(conv_kernel, DM / CV_CPB, CV_THREADS, CV_SMEM, 1, (const uint4*)h_sym[7] + SEQ / 8, (const float4*)h_sym[4] + SEQ / 2, (const bf16*)h_sym[8], (bf16*)h_sym[10], (const uint4*)h_sym[0], h_tmOut); break;
        default: break;
    }
}
static int n_stage_kernels() { return 9; }
static const char* stage_name(int k) { const char* n[] = {"kgen", "a1", "a2", "conv", "tr", "a1", "a2", "conv", "tr"}; return n[k]; }

extern "C" void kernel_launch(void* const* d_in, const int* in_sizes, int n_in, void* d_out, int out_size) {
    (void)in_sizes; (void)n_in; (void)out_size;
    static const void *p_in = nullptr, *p_w1 = nullptr, *p_w2 = nullptr, *p_out = nullptr;
    if (p_in != d_in[0] || p_w1 != d_in[1] || p_w2 != d_in[2] || p_out != d_out) {
        cudaFuncSetAttribute(conv_kernel, cudaFuncAttributeMaxDynamicSharedMemorySize, CV_SMEM);
        cudaFuncSetAttribute(a1_kernel<true>, cudaFuncAttributeMaxDynamicSharedMemorySize, A1_SMEM);
        cudaFuncSetAttribute(a1_kernel<false>, cudaFuncAttributeMaxDynamicSharedMemorySize, A1_SMEM);
        int dev; cudaGetDevice(&dev); cudaDeviceGetAttribute(&h_nsm, cudaDevAttrMultiProcessorCount, dev);
        if (h_nsm != 132) h_nsm = 128;
        cudaGetSymbolAddress(&h_sym[0], g_tap); cudaGetSymbolAddress(&h_sym[1], g_wq); cudaGetSymbolAddress(&h_sym[2], g_wo);
        cudaGetSymbolAddress(&h_sym[3], g_halo); cudaGetSymbolAddress(&h_sym[4], g_sum); cudaGetSymbolAddress(&h_sym[5], g_csp); cudaGetSymbolAddress(&h_sym[6], g_of);
        cudaGetSymbolAddress(&h_sym[7], g_piv); cudaGetSymbolAddress(&h_sym[8], g_x1T); cudaGetSymbolAddress(&h_sym[9], g_xcT); cudaGetSymbolAddress(&h_sym[10], g_yT);
        for (int i = 0; i < 264; i++) {
            const int s = i % 132, h = (s - 64) >> 1;
            const int t = h_nsm != 132 ? s : s < 64 ? ((s >> 1) & 7) * 16 + (s >> 4) * 2 + (s & 1) : s < 120 ? (1 + h % 7) * 16 + 8 + (h / 7) * 2 + (s & 1) : s < 124 ? 128 : s - 116;
            const int hg = (4 * (t >> 6) + (t & 3)) & 7;
            const uint64_t wp = (uint64_t)h_sym[1] + hg * 10 * WQ_STAGE;
            h_tab[i / 132].e[s] = make_uint4((uint32_t)wp, (uint32_t)(wp >> 32), ((t >> 2) & 15) | (i / 132) << 4 | hg << 8 | 5 * (hg >> 2) << 16 | (uint32_t)t << 24, 0);
        }
        void *px1, *px2;
        cudaGetSymbolAddress(&px1, g_x1T); cudaGetSymbolAddress(&px2, g_xcT);
        make_tmap(&h_tmX0, d_in[0], 128 * 640, 64, 64, 64, CU_TENSOR_MAP_SWIZZLE_128B, 1280, 640, 0);
        make_tmap(&h_tmX1, px2, 128, 64 * XCP, 64, 64, CU_TENSOR_MAP_SWIZZLE_128B, XCP, 64, 0);
        make_tmap(&h_tmR0, d_in[0], 640, 1024, 80, 64, CU_TENSOR_MAP_SWIZZLE_NONE, 1280, 640, 1);
        make_tmap(&h_tmR1, px2, 64, 640, 64, 80, CU_TENSOR_MAP_SWIZZLE_128B, XCP, 64, 1);
        make_tmap(&h_tmX1st, px1, 2048, 640, 64, 80, CU_TENSOR_MAP_SWIZZLE_128B, XCP);
        make_tmap(&h_tmW.q, d_in[1], 16, 640, 16, 32, CU_TENSOR_MAP_SWIZZLE_32B, 1920, 16, 5);
        make_tmap(&h_tmW.o, d_in[2], 640, 640, 4, 0, CU_TENSOR_MAP_SWIZZLE_32B);
        make_tmap(&h_tmW.t, d_in[2], 640, 640, 2, 0, CU_TENSOR_MAP_SWIZZLE_32B);
        make_tmap(&h_tmOut, d_out, 640, 1024, 80, 8, CU_TENSOR_MAP_SWIZZLE_NONE, 1280, 640, 1);
        p_in = d_in[0]; p_w1 = d_in[1]; p_w2 = d_in[2]; p_out = d_out;
    }
    for (int k = 0; k < n_stage_kernels(); k++) launch_stage(k, d_in, d_out);
}
```

```cpp
#include <cuda_runtime.h>
#include <cuda_bf16.h>
#include <cuda_fp16.h>
#include <stdint.h>
#include <cuda.h>

typedef __nv_bfloat16 bf16;

constexpr int SEQ = 2048;
constexpr int DM = 640;
constexpr int NMODE = 192;

__device__ __forceinline__ float bf2f(bf16 v) { return __bfloat162float(v); }
__device__ __forceinline__ float rbf(float v) {
    uint32_t r;
    asm("cvt.rn.bf16x2.f32 %0, %1, %2;" : "=r"(r) : "f"(v), "f"(0.f));
    return __uint_as_float(r);
}
__device__ __forceinline__ uint32_t pack2(float lo, float hi) {
    __nv_bfloat162 t = __floats2bfloat162_rn(lo, hi);
    return *reinterpret_cast<uint32_t*>(&t);
}
__device__ __forceinline__ void pdl_sync() {
    asm volatile("griddepcontrol.wait;" ::: "memory");
    asm volatile("griddepcontrol.launch_dependents;" ::: "memory");
}
__device__ __forceinline__ float sqrt_apx(float v) { float r; asm("sqrt.approx.ftz.f32 %0, %1;" : "=f"(r) : "f"(v)); return r; }
__device__ __forceinline__ float rcp_apx(float v) { float r; asm("rcp.approx.ftz.f32 %0, %1;" : "=f"(r) : "f"(v)); return r; }
__device__ __forceinline__ uint32_t smem_u32(const void* p) { return (uint32_t)__cvta_generic_to_shared(p); }

constexpr int TAPB = 2944, TAPE = 928;
__device__ __align__(128) uint4 g_tap[DM * TAPB / 16];
#define XPAD 64
constexpr int XCP = SEQ + XPAD;
__device__ __align__(128) bf16 g_x1T[DM * XCP];
__device__ __align__(128) bf16 g_xcT[DM * XCP];
__device__ __align__(128) uint4 g_of[128 * 1280];
constexpr int WQ_STAGE = 240 * 128, WOB = 80 * 160;
__device__ __align__(128) uint4 g_wq[8 * 10 * WQ_STAGE / 16];
__device__ __align__(128) uint4 g_wo[64 * WOB / 16];
__device__ __align__(128) uint4 g_xb[128 * 240];
__device__ __align__(16) float g_csp[10 * 1920];
#define FSTR 32
__device__ __align__(128) float2 g_sum[2 * SEQ + 256 * FSTR];
__device__ __align__(16) bf16 g_piv[2 * SEQ];
__device__ __align__(128) bf16 g_yT[DM * XCP];
__device__ uint32_t g_epoch;
__device__ __align__(16) unsigned long long g_rstat[SEQ];
__device__ __align__(128) uint4 g_halo[640 * 148];
__device__ __forceinline__ unsigned long long tagw(uint32_t payload, uint32_t tag) { return ((unsigned long long)tag << 32) | payload; }
__device__ __forceinline__ ulonglong2 ld_tag2(const ulonglong2* p) {
    ulonglong2 v;
    asm volatile("ld.relaxed.gpu.global.v2.u64 {%0, %1}, [%2];" : "=l"(v.x), "=l"(v.y) : "l"(p) : "memory");
    return v;
}
__device__ __forceinline__ bool tag_ok(ulonglong2 v, uint32_t tag) { return (uint32_t)(v.x >> 32) == tag && (uint32_t)(v.y >> 32) == tag; }
__device__ __forceinline__ uint32_t ld_epoch() { uint32_t v; asm volatile("ld.relaxed.gpu.global.u32 %0, [%1];" : "=r"(v) : "l"(&g_epoch) : "memory"); return v + 1; }
constexpr int SPIN_MAX = 1 << 20;
__device__ __align__(128) uint32_t g_started[11 * 32];
__device__ __forceinline__ void sm_started(int slot) { asm volatile("red.relaxed.gpu.global.add.u32 [%0], 1;" ::"l"(g_started + slot) : "memory"); }
__device__ __forceinline__ void publish(int slot) {
    asm volatile("fence.proxy.async.global;" ::: "memory");
    asm volatile("red.release.gpu.global.add.u32 [%0], 1;" ::"l"(g_started + slot) : "memory");
}
__device__ __forceinline__ void await_all(int slot, uint32_t want) {
#pragma unroll 1
    for (int it = 0; it < SPIN_MAX; it++) {
        uint32_t v;
        asm volatile("ld.acquire.gpu.global.u32 %0, [%1];" : "=r"(v) : "l"(g_started + slot) : "memory");
        if (__all_sync(~0u, (int)(v - want) >= 0)) break;
        __nanosleep(50);
    }
    asm volatile("fence.proxy.async.global;" ::: "memory");
}
__device__ __noinline__ void sm_idle(int slot) {
    if (threadIdx.x != 288) return;
    asm volatile("fence.acq_rel.gpu;" ::: "memory");
    asm volatile("fence.proxy.async.global;" ::: "memory");
    sm_started(slot);
    const uint32_t want = ld_epoch() * gridDim.x;
    pdl_sync();
#pragma unroll 1
    for (int it = 0; it < SPIN_MAX; it++) {
        uint32_t v;
        asm volatile("ld.relaxed.gpu.global.u32 %0, [%1];" : "=r"(v) : "l"(g_started + slot) : "memory");
        if ((int)(v - want) >= 0) break;
        __nanosleep(100);
    }
}
struct TileTab { uint4 e[132]; };
__device__ __forceinline__ bool elect() {
    uint32_t p;
    asm volatile("{\n.reg .pred p;\nelect.sync _|p, 0xffffffff;\nselp.b32 %0, 1, 0, p;\n}" : "=r"(p));
    return p;
}
#define DBG_SYMS
#define TSTAMP(i)
#define TSTAMP1(i)
#define TSTAMP1T(i, t)
#define TSTAMP1X(i, t)
#define SPAN(k, i)
#define GSTAMP(arr, i)
#define TSTAMP2(i)
#define TSTAMP3(i)
#define TSTAMP4(i)
#define TSTAMPK(i, t)
#define TSTAMPC(i)
#define DBGC(i)
#define DBGV(i, v)
#define DBGCAL(i)

#define CSK(i)
#define CSK_END
#define CSA(i)
#define CSA_END
#define CST(i)
#define CST_END
#define CST_EXTRA 0
__device__ __forceinline__ void mma_bf16(float* d, uint32_t a0, uint32_t a1, uint32_t a2, uint32_t a3, uint32_t b0, uint32_t b1) {
    asm volatile("mma.sync.aligned.m16n8k16.row.col.f32.bf16.bf16.f32 {%0,%1,%2,%3}, {%4,%5,%6,%7}, {%8,%9}, {%0,%1,%2,%3};"
                 : "+f"(d[0]), "+f"(d[1]), "+f"(d[2]), "+f"(d[3]) : "r"(a0), "r"(a1), "r"(a2), "r"(a3), "r"(b0), "r"(b1));
}
__device__ __forceinline__ void mma_bf16_k8(float* d, uint32_t a0, uint32_t a1, uint32_t b0) {
    asm volatile("mma.sync.aligned.m16n8k8.row.col.f32.bf16.bf16.f32 {%0,%1,%2,%3}, {%4,%5}, {%6}, {%0,%1,%2,%3};"
                 : "+f"(d[0]), "+f"(d[1]), "+f"(d[2]), "+f"(d[3]) : "r"(a0), "r"(a1), "r"(b0));
}
__device__ __forceinline__ void ldsm_x4(uint32_t* r, uint32_t addr) {
    asm volatile("ldmatrix.sync.aligned.m8n8.x4.shared.b16 {%0,%1,%2,%3}, [%4];"
                 : "=r"(r[0]), "=r"(r[1]), "=r"(r[2]), "=r"(r[3]) : "r"(addr));
}

__device__ __forceinline__ void ldsm_x4_t(uint32_t* r, uint32_t addr) {
    asm volatile("ldmatrix.sync.aligned.m8n8.x4.trans.shared.b16 {%0,%1,%2,%3}, [%4];"
                 : "=r"(r[0]), "=r"(r[1]), "=r"(r[2]), "=r"(r[3]) : "r"(addr));
}
__device__ __forceinline__ void mbar_init(uint32_t bar, int count) { asm volatile("mbarrier.init.shared::cta.b64 [%0], %1;" ::"r"(bar), "r"(count)); }
__device__ __forceinline__ void mbar_arrive(uint32_t bar) { asm volatile("mbarrier.arrive.shared::cta.b64 _, [%0];" ::"r"(bar) : "memory"); }
__device__ __forceinline__ void mbar_wait(uint32_t bar, uint32_t parity) {
    asm volatile("{\n.reg .pred p;\nWAIT_LOOP:\n"
                 "mbarrier.try_wait.parity.shared::cta.b64 p, [%0], %1;\n"
                 "@p bra.uni WAIT_DONE;\nbra.uni WAIT_LOOP;\nWAIT_DONE:\n}" ::"r"(bar), "r"(parity) : "memory");
}

__device__ __forceinline__ void mbar_expect_tx(uint32_t bar, uint32_t bytes) {
    asm volatile("mbarrier.arrive.expect_tx.shared::cta.b64 _, [%0], %1;" ::"r"(bar), "r"(bytes) : "memory");
}
__device__ __forceinline__ void tma_load_2d(uint32_t dst, const void* tmap, int c0, int c1, uint32_t bar) {
    asm volatile("cp.async.bulk.tensor.2d.shared::cluster.global.mbarrier::complete_tx::bytes [%0], [%1, {%3, %4}], [%2];"
                 ::"r"(dst), "l"(tmap), "r"(bar), "r"(c0), "r"(c1) : "memory");
}
__device__ __forceinline__ void tma_load_3d(uint32_t dst, const void* tmap, int c0, int c1, int c2, uint32_t bar) {
    asm volatile("cp.async.bulk.tensor.3d.shared::cluster.global.mbarrier::complete_tx::bytes [%0], [%1, {%3, %4, %5}], [%2];"
                 ::"r"(dst), "l"(tmap), "r"(bar), "r"(c0), "r"(c1), "r"(c2) : "memory");
}
__device__ __forceinline__ void fence_async_smem() { asm volatile("fence.proxy.async.shared::cta;" ::: "memory"); }
__device__ __forceinline__ void bulk_load(uint32_t dst, const void* src, uint32_t bytes, uint32_t bar) {
    asm volatile("cp.async.bulk.shared::cluster.global.mbarrier::complete_tx::bytes [%0], [%1], %2, [%3];"
                 ::"r"(dst), "l"(src), "r"(bytes), "r"(bar) : "memory");
}
__device__ __forceinline__ void stsm_x4(uint32_t addr, uint32_t r0, uint32_t r1, uint32_t r2, uint32_t r3) {
    asm volatile("stmatrix.sync.aligned.m8n8.x4.shared.b16 [%0], {%1,%2,%3,%4};" ::"r"(addr), "r"(r0), "r"(r1), "r"(r2), "r"(r3) : "memory");
}
__device__ __forceinline__ void stsm_x4_t(uint32_t addr, uint32_t r0, uint32_t r1, uint32_t r2, uint32_t r3) {
    asm volatile("stmatrix.sync.aligned.m8n8.x4.trans.shared.b16 [%0], {%1,%2,%3,%4};" ::"r"(addr), "r"(r0), "r"(r1), "r"(r2), "r"(r3) : "memory");
}
__device__ __forceinline__ void prefetch_tmap(const void* tmap) { asm volatile("prefetch.tensormap [%0];" ::"l"(tmap) : "memory"); }

__device__ __forceinline__ float2 cexp_at(float wr2, float wi, float p) {
    float er;
    asm("ex2.approx.ftz.f32 %0, %1;" : "=f"(er) : "f"(wr2 * p));
    float th = wi * p;
    const float k = rintf(th * 0.15915494309189535f);
    th = fmaf(k, -6.2831854820251465f, th);
    th = fmaf(k, 1.7484555314695172e-7f, th);
    return make_float2(er * __cosf(th), er * __sinf(th));
}
__device__ __forceinline__ float2 cmul(float2 a, float2 b) {
    return make_float2(fmaf(a.x, b.x, -a.y * b.y), fmaf(a.x, b.y, a.y * b.x));
}
__device__ __forceinline__ float2 csqr(float2 a) { return make_float2(fmaf(a.x, a.x, -a.y * a.y), (a.x + a.x) * a.y); }
__device__ __forceinline__ uint32_t packh(float2 v) {
    uint32_t r;
    asm("cvt.rn.f16x2.f32 %0, %1, %2;" : "=r"(r) : "f"(v.y), "f"(v.x));
    return r;
}
__device__ __forceinline__ uint2 packr(float2 v) { return make_uint2(packh(v), packh(make_float2(-v.y, v.x))); }
__device__ __forceinline__ uint32_t hcmul(uint32_t a, uint2 b) {
    const __half2 x = *reinterpret_cast<const __half2*>(&a);
    const __half2 r = __hfma2(__high2half2(x), *reinterpret_cast<const __half2*>(&b.y), __hmul2(__low2half2(x), *reinterpret_cast<const __half2*>(&b.x)));
    return *reinterpret_cast<const uint32_t*>(&r);
}

struct Par { const bf16 *logA, *Aim, *Cre, *Cim, *logdt, *dsk; int layer, pad; const bf16* x; uint4 *sum, *wop, *of, *halo, *tap; float* csp; uint4* wq; const bf16 *wqkv, *wo; };
struct KgMaps { CUtensorMap q, o, t; };

__device__ __forceinline__ void bulk_prefetch(const void* p, uint32_t bytes) { asm volatile("cp.async.bulk.prefetch.L2.global [%0], %1;" ::"l"(p), "r"(bytes) : "memory"); }
__device__ __forceinline__ void bulk_store(void* dst, uint32_t src, uint32_t bytes) { asm volatile("cp.async.bulk.global.shared::cta.bulk_group [%0], [%1], %2;" ::"l"(dst), "r"(src), "r"(bytes) : "memory"); }
__device__ __forceinline__ void kgen_first(const Par& in, const KgMaps& tm, const uint32_t b0, const uint32_t wbar, const bool one) {
    const uint32_t blk = blockIdx.x, sec = (blk >= 40) + (blk >= 80), it = (blk >> 3) - 5 * sec, up = (blk >> 2) & 1, hi = blk >> 6;
    auto fetch = [&](int h) {
        if (blk < 120) asm volatile("cp.async.bulk.tensor.4d.shared::cluster.global.mbarrier::complete_tx::bytes [%0], [%1, {%3, %3, %4, %5}], [%2];"
                                    ::"r"(b0 + 10240 * h), "l"(&tm.q), "r"(wbar + 8 * h), "r"(0), "r"(sec * 40 + (blk & 7) * 5), "r"(2 * it + 10 * (up ^ h)) : "memory");
    };
    auto fetch_o = [&](int i) {
        asm volatile("cp.async.bulk.tensor.5d.shared::cluster.global.mbarrier::complete_tx::bytes [%0], [%1, {%3, %3, %4, %3, %5}], [%2];"
                     ::"r"(b0 + 20480 + i * 5120), "l"(&tm.o + i), "r"(wbar + 16), "r"(0), "r"((blk & 7) * 10 + (hi + i) * 4), "r"(((blk >> 3) & 7) * 5) : "memory");
    };
    if (one) {
#pragma unroll
        for (int i = 0; i < 3; i++) mbar_init(wbar + 8 * i, 1);
        asm volatile("fence.mbarrier_init.release.cluster;" ::: "memory");
        fetch(0);
    }
    __syncwarp();
    if (blk >> 20) __trap();
    if (one) {
        bulk_prefetch(in.wqkv + blk * 9600, 19200);
        fetch(1);
        bulk_prefetch(in.wo + blk * 3200, 6400);
        fetch_o(0);
        if (hi) fetch_o(1);
        mbar_expect_tx(wbar, 10240); mbar_expect_tx(wbar + 8, 10240); mbar_expect_tx(wbar + 16, 5120 + hi * 2560);
        bulk_prefetch(in.x + blk * 10240, 20480);
    }
}
__device__ __forceinline__ void kgen_side(const Par& in, const uint32_t b0, const uint32_t wbar) {
    const uint32_t blk = blockIdx.x, sec = (blk >= 40) + (blk >= 80), it = (blk >> 3) - 5 * sec, cg = (blk >> 3) & 7, hb = blk & 7;
    unsigned char* dst = reinterpret_cast<unsigned char*>(in.wq) + (hb * 10 + it) * WQ_STAGE + sec * 5120;
    if (blk < 120) {
        mbar_wait(wbar, 0);
        CSK(2);
        bulk_store(dst, b0, 5120); bulk_store(dst + 15360, b0 + 5120, 5120);
        mbar_wait(wbar + 8, 0);
        CSK(3);
        bulk_store(dst + 5 * WQ_STAGE, b0 + 10240, 5120); bulk_store(dst + 5 * WQ_STAGE + 15360, b0 + 15360, 5120);
        asm volatile("cp.async.bulk.commit_group;" ::: "memory");
        asm volatile("cp.async.bulk.wait_group 0;" ::: "memory");
        CSK(4);
        publish(96 + 32 * hb);
        CSK(5);
    }
    if (blk < 128) {
        mbar_wait(wbar + 16, 0);
        bulk_store(reinterpret_cast<unsigned char*>(in.wop) + (cg * 8 + (hb == cg ? 0 : hb + (hb < cg))) * WOB + (blk >> 6) * 5120, b0 + 20480, blk < 64 ? 5120 : 7680);
        asm volatile("cp.async.bulk.commit_group;" ::: "memory");
    }
}
__device__ __forceinline__ void kgen_sums(const Par& in, const uint32_t b0, const int h) {
    const int lane = threadIdx.x & 31, blk = blockIdx.x;
    if (blk < 120) {
        float cs[5][4] = {};
#pragma unroll
        for (int a = 0; a < 4; a++)
#pragma unroll
            for (int j = 0; j < 5; j++) {
                uint32_t w[4];
                ldsm_x4_t(w, b0 + h * 10240 + j * 1024 + ((lane >> 4) * 8 + (lane & 7)) * 32 + ((((lane >> 3) ^ (lane >> 2)) & 1) << 4) + (a >> 1) * 5120 + (a & 1) * 512);
                mma_bf16(cs[j], w[0], w[1], w[2], w[3], 0x3f803f80u, 0x3f803f80u);
            }
#pragma unroll
        for (int j = 0; j < 5; j++)
            if ((lane & 3) < 2) in.csp[(blk + 120 * h) * 80 + j * 16 + (lane >> 2) + 8 * (lane & 3)] = (lane & 3) ? cs[j][2] : cs[j][0];
    }
}
struct KgPar { uint32_t pw[4], ph[4], pdt, pdsk; };
__device__ __forceinline__ void kgen_load(const Par& in, const bf16* logA, const int w11, KgPar& k) {
    const uint32_t o = blockIdx.x * 480 + min(w11 * 48, w11 * 32 + 128), ow = o + (threadIdx.x & 31), oh = o + ow + (w11 < 8 ? 64 : 0);
    k.pdt = reinterpret_cast<const unsigned short*>(in.logdt)[ow / 96];
    k.pdsk = reinterpret_cast<const unsigned short*>(in.dsk)[ow / 96];
#pragma unroll
    for (int i = 0; i < 4; i++) {
        const bf16* p = i == 0 ? logA : i == 1 ? in.Aim : i == 2 ? in.Cre : in.Cim;
        k.pw[i] = reinterpret_cast<const uint32_t*>(p)[ow]; k.ph[i] = reinterpret_cast<const unsigned short*>(p)[oh];
    }
}
__device__ __forceinline__ void kgen_tables(const Par& in, uint4* tabs, const int w11, const KgPar& kp) {
    const int lane = threadIdx.x & 31, grp = min(w11 >> 1, 4), warp = w11 - 2 * grp;
    const int blk = blockIdx.x, d = blk * 5 + grp, tid = warp * 32 + lane;
    uint4* tab = tabs + grp * (2 * 256);
    const uint32_t *pw = kp.pw, *ph = kp.ph;
#pragma unroll
    for (int i = 0; i < 3; i++)
        if (i < 2 || w11 * 32 + lane < 36) asm volatile("st.global.v4.u32 [%0], {%1,%1,%1,%1};" ::"l"(in.halo + blk * 740 + w11 * 32 + lane + 352 * i), "r"(~0u));
    __syncwarp();
    if (w11 == 10) {
        if (lane < 16) in.sum[blk * 16 + lane] = make_uint4(0, 0, 0, 0);
        else if (lane < 20) reinterpret_cast<uint32_t*>(in.sum + 2048)[(blk * 4 + lane - 16) * FSTR] = 0;
    } else if (w11 > 1) asm volatile("bar.arrive 9, 352;" ::: "memory");
#pragma unroll
    for (int i = 0; i < 6; i++) tabs[w11 * 256 + 32 * i + lane] = make_uint4(0, 0, 0, 0);
    __syncwarp();
    CSK(1);
    const uint32_t tw = smem_u32(tabs) + w11 * 4096;
    const int g = lane >> 2, t = lane & 3;
    const int mt = lane >> 3, r = lane & 7;
    const uint32_t st1 = tw + mt * 1024 + r * 16, st2 = tw + (mt & 1) * 1024 + (mt >> 1) * 128 + ((r ^ (mt >> 1)) << 4), st3 = tw + 2048 + mt * 128 + ((r ^ mt) << 4);
    const uint32_t lda = tw + (mt & 1) * 1024 + r * 128 + (((mt >> 1) ^ r) << 4), ldb = tw + (mt >> 1) * 1024 + r * 128 + (((mt & 1) ^ r) << 4), ldc = tw + 2048 + r * 128 + ((mt ^ r) << 4);
    auto ldsm = [](uint32_t* v, uint32_t a) {
        asm volatile("ldmatrix.sync.aligned.m8n8.x4.shared.b16 {%0,%1,%2,%3}, [%4];" : "=r"(v[0]), "=r"(v[1]), "=r"(v[2]), "=r"(v[3]) : "r"(a) : "memory");
    };
    auto mma = [](float* c, const uint32_t* a, const uint32_t* b) {
        asm("mma.sync.aligned.m16n8k16.row.col.f32.f16.f16.f32 {%0,%1,%2,%3}, {%4,%5,%6,%7}, {%8,%9}, {%0,%1,%2,%3};"
            : "+f"(c[0]), "+f"(c[1]), "+f"(c[2]), "+f"(c[3]) : "r"(a[0]), "r"(a[1]), "r"(a[2]), "r"(a[3]), "r"(b[0]), "r"(b[1]));
    };
    asm volatile("st.shared.u32 [%0], %1;" ::"r"(tw + 3072), "r"(st1 ^ st2 ^ st3 ^ lda ^ ldb ^ ldc) : "memory");
    if (in.pad) __trap();
    const float dt = rbf(expf(__uint_as_float(kp.pdt << 16)));
    const uint32_t cm = __vmaxu2(__vmaxu2(pw[2] & 0x7fff7fffu, pw[3] & 0x7fff7fffu), __byte_perm(ph[2], ph[3], 0x5410) & 0x7fff7fffu);
    const int ex = min(max((int)(__float_as_uint(__uint_as_float(__reduce_max_sync(~0u, max(cm << 16, cm & 0xffff0000u))) * dt) >> 23), 20), 240);
    const float scale = __uint_as_float((uint32_t)(127 + 10 + 127 - ex) << 23), unscale = 2.0f * __uint_as_float((uint32_t)(ex - 10) << 23);
    float k2048 = 0.f;
    float acc[5][4] = {};
    uint32_t af[4][4] = {};
    auto rest = [&] {
        uint32_t b[4][4], c[8];
#pragma unroll
        for (int k = 0; k < 4; k++) {
            ldsm(b[k], ldb ^ (k << 5));
            if (!(k & 1)) ldsm(c + 2 * k, ldc ^ (k << 5));
        }
#pragma unroll
        for (int k = 0; k < 4; k++) { mma(acc[2], af[k], b[k]); mma(acc[3], af[k], b[k] + 2); mma(acc[4], af[k], c + 2 * k); }
    };
#pragma unroll 1
    for (uint32_t sel = 0x1076; sel < (grp < 4 ? 0x6000u : 0x4000u); sel += 0x2200) {
        rest();
        auto par = [&](int i) { return __uint_as_float(__byte_perm(pw[i], ph[i], sel)); };
        const float wr2 = -rbf(expf(par(0))) * dt * 1.4426950408889634f, wi = par(1) * dt;
        const float2 y1 = cexp_at(wr2, -wi, 1.f), w64 = cexp_at(wr2, wi, 64.f), y4 = csqr(csqr(y1)), z8 = csqr(make_float2(y4.x, -y4.y)), y128 = csqr(make_float2(w64.x, -w64.y));
        float2 h0 = make_float2(1.f, 0.f), g0 = make_float2(par(2) * dt * scale, -par(3) * dt * scale);
        const float2 v2 = csqr(y128), v3 = cmul(v2, y128), v4 = csqr(v2), v8 = csqr(v4), c8 = cmul(g0, v8);
        const uint2 z64 = packr(w64), v[8] = {make_uint2(packh(c8), 0u), packr(y128), packr(v2), packr(v3), packr(v4), packr(cmul(v4, y128)), packr(csqr(v3)), packr(cmul(v4, v3))};
        k2048 += fmaf(c8.x, v8.x, -c8.y * v8.y);
        uint32_t ge[4];
#pragma unroll
        for (int e = 0; e < 8; e++) {
            const uint32_t p = packh(h0), q = packh(g0);
            if (!(e & 1)) ge[e >> 1] = q;
            stsm_x4((st1 ^ (e << 4)) + e * 128, p, e ? hcmul(p, z64) : z64.x, q, hcmul(q, v[1]));
            if (e < 7) { h0 = e ? cmul(h0, z8) : z8; g0 = cmul(g0, y1); }
        }
        __syncwarp();
        uint32_t b[4][4];
#pragma unroll
        for (int k = 0; k < 4; k++) { ldsm(af[k], lda ^ (k << 5)); ldsm(b[k], (ldb ^ (k << 5)) + 2048); }
#pragma unroll
        for (int e = 0; e < 8; e += 2) {
            stsm_x4((st2 ^ (e << 4)) + e * 128, hcmul(ge[e & 3], v[2 + (e >> 2)]), hcmul(ge[0], v[4 + (e >> 1)]), hcmul(ge[(e & 3) + 1], v[2 + (e >> 2)]), hcmul(ge[2], v[4 + (e >> 1)]));
            if (!(e & 3)) stsm_x4((st3 ^ (e << 4)) + e * 128, e ? hcmul(v[0].x, v[e]) : v[0].x, hcmul(v[0].x, v[e + 1]), hcmul(v[0].x, v[e + 2]), hcmul(v[0].x, v[e + 3]));
            mma(acc[0], af[e >> 1], b[e >> 1]);
            mma(acc[1], af[e >> 1], b[e >> 1] + 2);
        }
        __syncwarp();
        if (sel == 0x1076) CSK(3);
    }
    rest();
#pragma unroll
    for (int e = 0; e < 5; e++) k2048 += __shfl_xor_sync(~0u, k2048, 1 << e);
    {
        float* Pp = reinterpret_cast<float*>(tab + warp * 256);
        auto sw = [](int i) { return i ^ ((i >> 2) & 24); };
#pragma unroll
        for (int h = 0; h < 2; h++) {
            const int b = g + 8 * h;
            *reinterpret_cast<float2*>(Pp + sw(8 * b + 2 * t)) = make_float2(acc[0][2 * h] * unscale, acc[0][2 * h + 1] * unscale);
            *reinterpret_cast<float2*>(Pp + 128 + sw(8 * b + 2 * t)) = make_float2(acc[1][2 * h] * unscale, acc[1][2 * h + 1] * unscale);
            *reinterpret_cast<float2*>(Pp + 256 + sw(4 * b + 2 * (t & 1) + 64 * (t >> 1))) = make_float2(acc[2][2 * h] * unscale, acc[2][2 * h + 1] * unscale);
            *reinterpret_cast<float2*>(Pp + 384 + sw(2 * b + 32 * t)) = make_float2(acc[3][2 * h] * unscale, acc[3][2 * h + 1] * unscale);
            Pp[512 + sw(b + 32 * t)] = acc[4][2 * h] * unscale;
            Pp[512 + sw(b + 32 * t + 16)] = acc[4][2 * h + 1] * unscale;
        }
        if (lane == 0) Pp[640] = k2048 * unscale;
    }
    CSK(4);
    asm volatile("bar.sync %0, %1;" ::"r"(grp + 4), "r"(grp < 4 ? 64 : 96) : "memory");
    if (warp == 2) return;
    const float* Kp = reinterpret_cast<const float*>(tab);
    auto ksum = [&](int i) -> float { return rbf(Kp[i] + Kp[1024 + i] + (grp < 4 ? 0.f : Kp[2048 + i])); };
    auto ksum2 = [&](int q) -> float2 {
        q ^= (q >> 2) & 12;
        const float2 a = reinterpret_cast<const float2*>(Kp)[q], b = reinterpret_cast<const float2*>(Kp)[512 + q];
        const float2 c = grp < 4 ? make_float2(0.f, 0.f) : reinterpret_cast<const float2*>(Kp)[1024 + q];
        return make_float2(a.x + b.x + c.x, a.y + b.y + c.y);
    };
    {
        uint2* W2 = reinterpret_cast<uint2*>(in.tap + d * (TAPB / 16)) + 8;
        uint2* E4 = W2 + (TAPE - 64) / 8;
        float2 v = ksum2(64 * warp + lane), z = ksum2(64 * warp + 32 + lane), y = ksum2(128 + tid);
        const int q = (96 + tid) ^ (((96 + tid) >> 2) & 6);
        const float4 ua = reinterpret_cast<const float4*>(Kp)[q], uc = reinterpret_cast<const float4*>(Kp)[256 + q], ud = grp < 4 ? make_float4(0.f, 0.f, 0.f, 0.f) : reinterpret_cast<const float4*>(Kp)[512 + q];
        const float4 ub = make_float4(uc.x + ud.x, uc.y + ud.y, uc.z + ud.z, uc.w + ud.w);
        const float s1 = ksum(tid == 31 ? 336 : lane ? 384 : 103), s2 = ksum(tid == 31 ? 512 : tid ? 640 : 231);
        if (tid == 0) v.x += __uint_as_float(kp.pdsk << 16);
        if (tid == 63) y.y -= s1;
        const uint32_t lo = pack2(v.x, v.y), hi = pack2(z.x, z.y), tp = pack2(y.x, y.y);
        uint32_t nl = __shfl_sync(~0u, lo, lane - 1), nh = __shfl_sync(~0u, lane == 31 ? lo : hi, lane - 1), nt = __shfl_sync(~0u, tp, lane + 1);
        if (lane == 0) nl = warp ? __float_as_uint(s1) : 0u;
        if (lane == 31) nt = warp ? 0u : __float_as_uint(s1) >> 16;
        W2[64 * warp + lane] = make_uint2(__byte_perm(lo, nl, 0x7610), __byte_perm(lo, 0, 0x1032));
        W2[64 * warp + lane + 32] = make_uint2(__byte_perm(hi, nh, 0x7610), __byte_perm(hi, 0, 0x1032));
        reinterpret_cast<uint4*>(W2)[64 + tid] = make_uint4(__byte_perm(tp, __float_as_uint(s2), tid ? 0x1010 : 0x7610), __byte_perm(tp, 0, 0x1010), __byte_perm(tp, 0, 0x1032), __byte_perm(nt, tp, 0x7610));
        E4[(tid < 32 ? 159 : 209 - 32) + tid] = make_uint2(pack2(ua.x + ub.x, ua.y + ub.y), pack2(ua.z + ub.z, ua.w + ub.w - (tid == 31 ? s2 : 0.f)));
        if (tid == 63) E4[241] = make_uint2(__float_as_uint(s2) >> 16, 0u);
    }
    CSK(5);
    SPAN(0, 3);
}

#define CV_SLEEP 40
#define CV_LD "ld.relaxed.gpu.global"
#define CV_NL 1
#define CV_D2 3
#define CV_PDH 12
#define CV_PDF 4
#define CV_HAND 7
constexpr int CV_CPB = 5;
constexpr int CV_THREADS = 512;
constexpr int UPADF = 128;
constexpr int ULEN = UPADF + SEQ;
constexpr int XLEN = XCP;
constexpr int BX_5 = 0, BX_3 = 3264, BX_9 = 6528, BX_7 = 8960, BX_LEN = 11392;
constexpr int CV_SM_U = 0;
constexpr int CV_SM_T = CV_CPB * ULEN * 2;
constexpr int CV_SM_B = CV_SM_T + CV_CPB * TAPB;
constexpr int CV_SM_X = CV_SM_B + CV_CPB * BX_LEN;
constexpr int CV_SM_Y = (CV_SM_X + CV_CPB * XLEN * 2 + 127) & ~127;
constexpr int CV_SM_CNT = CV_SM_Y + CV_CPB * 8192;
constexpr int CV_SM_O = CV_SM_CNT + 128;
constexpr int CV_SMEM = CV_SM_O + 20480 + CST_EXTRA;
static_assert(ULEN % 128 == 0 && CV_SM_B % 128 == 0 && CV_SM_CNT % 128 == 0, "layout");

__device__ __forceinline__ uint32_t sub2(uint32_t x, uint32_t m) {
    const __nv_bfloat162 d = __hsub2(*reinterpret_cast<const __nv_bfloat162*>(&x), *reinterpret_cast<const __nv_bfloat162*>(&m));
    return *reinterpret_cast<const uint32_t*>(&d);
}
__device__ __forceinline__ uint32_t add2(uint32_t x, uint32_t y) {
    const __nv_bfloat162 d = __hadd2_rn(*reinterpret_cast<const __nv_bfloat162*>(&x), *reinterpret_cast<const __nv_bfloat162*>(&y));
    return *reinterpret_cast<const uint32_t*>(&d);
}
__device__ __forceinline__ void wgmma_fence() { asm volatile("wgmma.fence.sync.aligned;" ::: "memory"); }
__device__ __forceinline__ void wgmma_commit() { asm volatile("wgmma.commit_group.sync.aligned;" ::: "memory"); }
template <int N> __device__ __forceinline__ void wgmma_wait() { asm volatile("wgmma.wait_group.sync.aligned %0;" ::"n"(N) : "memory"); }
__device__ __forceinline__ uint64_t make_desc(uint32_t addr, uint32_t lbo, uint32_t sbo, uint32_t mode) {
    return (uint64_t)((addr & 0x3FFFF) >> 4) | ((uint64_t)(lbo >> 4) << 16) | ((uint64_t)(sbo >> 4) << 32) | ((uint64_t)mode << 62);
}
__device__ __forceinline__ void wgmma_rs128(float (&d)[64], uint2 hi, uint2 lo, uint64_t db, int acc) {
    asm volatile("{\n.reg .pred p;\nsetp.ne.b32 p, %69, 0;\nwgmma.mma_async.sync.aligned.m64n128k16.f32.bf16.bf16 {%0,%1,%2,%3,%4,%5,%6,%7,%8,%9,%10,%11,%12,%13,%14,%15,%16,%17,%18,%19,%20,%21,%22,%23,%24,%25,%26,%27,%28,%29,%30,%31,%32,%33,%34,%35,%36,%37,%38,%39,%40,%41,%42,%43,%44,%45,%46,%47,%48,%49,%50,%51,%52,%53,%54,%55,%56,%57,%58,%59,%60,%61,%62,%63}, {%64,%65,%66,%67}, %68, p, 1, 1, 0;\n}"
                 : "+f"(d[0]), "+f"(d[1]), "+f"(d[2]), "+f"(d[3]), "+f"(d[4]), "+f"(d[5]), "+f"(d[6]), "+f"(d[7]), "+f"(d[8]), "+f"(d[9]), "+f"(d[10]), "+f"(d[11]), "+f"(d[12]), "+f"(d[13]), "+f"(d[14]), "+f"(d[15]), "+f"(d[16]), "+f"(d[17]), "+f"(d[18]), "+f"(d[19]), "+f"(d[20]), "+f"(d[21]), "+f"(d[22]), "+f"(d[23]), "+f"(d[24]), "+f"(d[25]), "+f"(d[26]), "+f"(d[27]), "+f"(d[28]), "+f"(d[29]), "+f"(d[30]), "+f"(d[31]), "+f"(d[32]), "+f"(d[33]), "+f"(d[34]), "+f"(d[35]), "+f"(d[36]), "+f"(d[37]), "+f"(d[38]), "+f"(d[39]), "+f"(d[40]), "+f"(d[41]), "+f"(d[42]), "+f"(d[43]), "+f"(d[44]), "+f"(d[45]), "+f"(d[46]), "+f"(d[47]), "+f"(d[48]), "+f"(d[49]), "+f"(d[50]), "+f"(d[51]), "+f"(d[52]), "+f"(d[53]), "+f"(d[54]), "+f"(d[55]), "+f"(d[56]), "+f"(d[57]), "+f"(d[58]), "+f"(d[59]), "+f"(d[60]), "+f"(d[61]), "+f"(d[62]), "+f"(d[63])
                 : "r"(hi.x), "r"(hi.y), "r"(lo.x), "r"(lo.y), "l"(db), "r"(acc));
}
template <int V> struct Int { __device__ constexpr operator int() const { return V; } };
__device__ __forceinline__ void sts4(uint32_t a, const uint32_t* v) { asm volatile("st.shared.v4.u32 [%0], {%1,%2,%3,%4};" ::"r"(a), "r"(v[0]), "r"(v[1]), "r"(v[2]), "r"(v[3]) : "memory"); }
__device__ __forceinline__ uint32_t lds1(uint32_t a) { uint32_t v; asm volatile("ld.shared.u32 %0, [%1];" : "=r"(v) : "r"(a) : "memory"); return v; }
__device__ __forceinline__ uint32_t lds1v(uint32_t a) { uint32_t v; asm volatile("ld.volatile.shared.u32 %0, [%1];" : "=r"(v) : "r"(a) : "memory"); return v; }
__device__ __forceinline__ uint4 lds4(uint32_t a) { uint4 v; asm volatile("ld.shared.v4.u32 {%0,%1,%2,%3}, [%4];" : "=r"(v.x), "=r"(v.y), "=r"(v.z), "=r"(v.w) : "r"(a) : "memory"); return v; }
__device__ __forceinline__ uint4 ldx(uint32_t a) {
    uint4 v;
    asm volatile("ld.shared.v2.u32 {%0,%1}, [%4];\nld.shared.v2.u32 {%2,%3}, [%4+128];" : "=r"(v.x), "=r"(v.y), "=r"(v.z), "=r"(v.w) : "r"(a) : "memory");
    return v;
}
__device__ __forceinline__ void cv_store(unsigned char* p, uint4 x, uint4 y) {
    asm volatile("st.relaxed.gpu.global.v2.u32 [%0], {%1,%2};" ::"l"(p), "r"(add2(x.x, __byte_perm(y.x, y.y, 0x5410))), "r"(add2(x.y, __byte_perm(y.z, y.w, 0x5410))) : "memory");
    asm volatile("st.relaxed.gpu.global.v2.u32 [%0], {%1,%2};" ::"l"(p + 128), "r"(add2(x.z, __byte_perm(y.x, y.y, 0x7632))), "r"(add2(x.w, __byte_perm(y.z, y.w, 0x7632))) : "memory");
}
__device__ __forceinline__ int usw(int ch) { return ch ^ ((ch >> 3) & 1); }
__global__ void __launch_bounds__(CV_THREADS, 1) conv_kernel(int layer, const uint4* __restrict__ piv, const float4* __restrict__ sum, const bf16* __restrict__ x1T,
                                                             bf16* __restrict__ dst, const uint4* __restrict__ tap, const __grid_constant__ CUtensorMap tmOut) {
    extern __shared__ __align__(1024) unsigned char sm[];
    SPAN(3 + 4 * layer, 0);
    bf16* Us = reinterpret_cast<bf16*>(sm + CV_SM_U);
    bf16* Xs = reinterpret_cast<bf16*>(sm + CV_SM_X);
#define CV_IDX int tid; asm volatile("mov.u32 %0, %tid.x;" : "=r"(tid)); const int lane = tid & 31, warp = __shfl_sync(~0u, tid >> 5, 0);
    const int d0 = blockIdx.x * CV_CPB, tile = blockIdx.x; (void)tile;
    const uint32_t cnt = smem_u32(sm + CV_SM_CNT);
    struct Lc { uint32_t a4, a8, uc, ud, y, e4, en, sp, ss; int go; };
    auto lane_consts = [&](int lane, int c) {
        const int mat = lane >> 3, r = lane & 7, g = lane >> 2, ti = lane & 3, e = g - 2 * ti;
        const int j2 = 13 + (r ^ 1) + 8 * (mat >> 1), j3 = j2 + 2, i0 = 8 * (mat & 1);
        const uint32_t sb = smem_u32(sm), oc = sb + usw(16 * (mat >> 1) + 2 * r + (mat & 1)) * 16;
        const Lc l = {sb + CV_SM_B + c * BX_LEN + ((j2 & 1) ? BX_3 + (4 * j2 + i0 + 84) * 2 : BX_5 + (4 * j2 + i0 + 80) * 2),
                      sb + CV_SM_B + c * BX_LEN + ((j3 & 1) ? BX_7 : BX_9) + (8 * j3 + i0 + 136) * 2,
                      oc + CV_SM_U + (c * ULEN + UPADF) * 2, sb + CV_SM_U + (c * ULEN + UPADF) * 2 + usw(16 * mat + 2 * r + 2) * 16, oc + CV_SM_Y + c * 8192,
                      sb + CV_SM_T + c * TAPB + TAPE + (307 + 2 * g - ti) * 4, sb + CV_SM_T + c * TAPB + (528 + e) * 4,
                      e == -5 ? 0x4410u : e == -4 ? 0x1044u : 0x4444u, e == 3 ? 0x4410u : e == 4 ? 0x1044u : 0x4444u,
                      c * XCP * 2 + (lane >> 4) * 256 + (lane & 15) * 8};
        asm volatile("st.shared.u32 [%0], %1;" ::"r"(sb + CV_SM_CNT + 120), "r"(l.y ^ l.a4 ^ l.a8 ^ l.uc ^ l.ud ^ l.e4 ^ l.en ^ l.sp ^ l.ss ^ l.go) : "memory");
        return l;
    };
    unsigned char* const dq = reinterpret_cast<unsigned char*>(dst + (size_t)d0 * XCP);
    auto far = [&](auto T0_, const auto& seq, const Lc& lc, int c, int lane, const uint2 (&f)[20], uint32_t kk) {
        constexpr int T0 = T0_, T1 = T0 + 6, TC = T0 > 7 ? T0 : 7, NS = sizeof(seq) / sizeof(seq[0]), PD = T0 > 7 ? CV_PDH : CV_PDF;
        uint32_t bq[28], yw[4], yz[4], P, S;
        uint4 xv, yv;
        asm("prmt.b32 %0, %1, 0, %2;" : "=r"(P) : "r"(kk), "r"(lc.sp));
        asm("prmt.b32 %0, %1, 0, %2;" : "=r"(S) : "r"(kk), "r"(lc.ss));
#pragma unroll
        for (int k = 0; 2 * k < T1 - TC + 4; k++) ldsm_x4(bq + 4 * k, lc.uc + (TC - 8) * 256 + 512 * k);
#pragma unroll
        for (int k = 0; 4 * k < T1 - TC; k++) ldsm_x4(bq + 20 + 4 * k, lc.ud + (TC - 8) * 256 + 1024 * k);
        CST(3);
        mbar_wait(cnt + 8 * c, 0);
        mbar_wait(cnt + 40, 0);
        CST(4);
        float acc[6][4] = {};
        uint32_t a[PD + 1][4];
#pragma unroll
        for (int i = -PD; i < NS + 3; i++) {
            if (i + PD < NS) ldsm_x4_t(a[(i + PD) % (PD + 1)], seq[i + PD] < 32 ? lc.a4 + (seq[i + PD] - 2) * 128 : lc.a8 + (seq[i + PD] - 34) * 256);
            if (i < 0) continue;
#pragma unroll
            for (int T = T0; T < T1; T++) {
                if (i >= NS) break;
                const int ee = seq[i] < 32 ? 2 * T - 6 - seq[i] : T + 35 - seq[i];
                if (i == 0 && T >= TC) mma_bf16(acc[T - T0], P, 0u, S, P, bq[2 * (T - TC)], bq[2 * (T - TC) + 1]);
                if (i == 1 && T >= TC) mma_bf16_k8(acc[T - T0], 0u, S, bq[20 + T - TC]);
                if (i == (T >= TC ? 2 : 0)) mma_bf16(acc[T - T0], f[19].x, 0u, f[19].y, f[19].x, bq[2 * (T - TC + 4)], bq[2 * (T - TC + 4) + 1]);
                if (seq[i] < 32 ? ee >= 0 && ee <= 9 : ee >= 10) mma_bf16(acc[T - T0], a[i % (PD + 1)][0], a[i % (PD + 1)][1], a[i % (PD + 1)][2], a[i % (PD + 1)][3], f[ee].x, f[ee].y);
            }
#pragma unroll
            for (int k = 0; k < 3; k++) {
                const int o = 256 * T0 + 512 * k;
                auto at = [&](int d) { return i - d >= 0 && i - d < NS && seq[i - d < 0 ? 0 : i - d < NS ? i - d : 0] == 2 * T0 + 4 * k - 4; };
                if (at(CV_D2)) {
                    cv_store(dq + lc.go + o, xv, yv);
                    if (layer > 19 - 2 * k) __trap();
                }
                if (at(-2)) { ldsm_x4_t(yw, lc.y + o); ldsm_x4_t(yz, lc.y + 3584 + o); }
                if (at(1)) {
#pragma unroll
                    for (int q = 0; q < 4; q++) yw[q] = add2(add2(yw[q], yz[q]), pack2(acc[2 * k + (q >> 1)][2 * (q & 1)], acc[2 * k + (q >> 1)][2 * (q & 1) + 1]));
                    stsm_x4_t(lc.y + o, yw[0], yw[1], yw[2], yw[3]);
                    xv = ldx(smem_u32(Xs) + lc.go + o);
                    __syncwarp();
                    yv = lds4(smem_u32(sm + CV_SM_Y) + c * 8192 + o + usw(lane) * 16);
                    if (layer > 20 - 2 * k) __trap();
                    if (k == 2) CST(6);
                }
            }
        }
    };
    TSTAMP1X(9, 256);
    if (threadIdx.x >= 256) {
        if (threadIdx.x < 288 && elect()) {
            mbar_init(cnt + 48, 1);
            asm volatile("fence.mbarrier_init.release.cluster;" ::: "memory");
            bulk_load(smem_u32(sm + CV_SM_T), tap + d0 * (TAPB / 16), CV_CPB * TAPB, cnt + 48);
            mbar_expect_tx(cnt + 48, CV_CPB * TAPB);
        }
        CV_IDX
        const int wgu = (warp >> 2) & 1, g = lane >> 2, ti = lane & 3;
        CST(1);
        if (warp > 8 && elect()) {
            if (warp < 15) mbar_init(cnt + 8 * (warp - 9), warp == 14 ? 8 : 4);
            else if (layer) prefetch_tmap(&tmOut);
        }
        if (warp < 13 && lane < 17 - (warp == 12)) {
            const int off = warp == 12 ? CV_SM_U : CV_SM_B + (warp == 11 ? BX_7 : (warp - 8) * BX_3), str = warp == 12 ? ULEN * 2 : BX_LEN;
#pragma unroll
            for (int c = 0; c < CV_CPB; c++) *reinterpret_cast<uint4*>(sm + off + c * str + 16 * lane) = make_uint4(0, 0, 0, 0);
        }
        fence_async_smem();
        asm volatile("bar.arrive 3, 512;" ::: "memory");
        asm volatile("bar.sync 1, 256;" ::: "memory");
        TSTAMP1X(10, 256);
        asm volatile("setmaxnreg.inc.sync.aligned.u32 168;");
        const uint32_t Tc = smem_u32(sm + CV_SM_T) + (16 + 128 * (warp & 2) + 8 * (warp & 1) + g - 2 * ti) * 4;
        uint2 fa[8][2], fn[8][2];
        auto near_taps = [&](uint2 (&f)[8][2], int c) {
#pragma unroll
            for (int m = 0; m < 16; m++) f[m >> 1][m & 1] = make_uint2(lds1v(Tc + c * TAPB + 64 * (m >> 1) - 32 * (m & 1)), lds1v(Tc + c * TAPB + 64 * (m >> 1) - 32 * (m & 1) + 512));
        };
        CST(6);
        mbar_wait(cnt + 48, 0);
        TSTAMP1X(11, 256); CST(5);
        near_taps(fa, 3 * wgu);
        near_taps(fn, 2 - wgu);
        const int hc = wgu ? warp & 3 : 4;
        const Lc lc = lane_consts(lane, hc);
        TSTAMP1X(12, 256); CST(0);
        uint32_t ya = smem_u32(sm + CV_SM_Y) + wgu * 8192 + (warp & 2) * 2048 + usw(2 * lane + (warp & 1)) * 16;
        uint64_t db = make_desc(smem_u32(Us + wgu * ULEN + UPADF), 16, 256, 3);
        if (wgu) { asm volatile("bar.sync 6, 384;" ::: "memory"); fence_async_smem(); }
        int c = wgu;
        auto chain = [&](const uint2 (&f)[8][2], auto&& meanwhile) {
            float acc[64];
            asm volatile("bar.sync %0, %1;" ::"r"(c ? 4 + wgu : 2), "r"(c ? 256 : 384) : "memory");
            TSTAMPC(1 + 3 * c);
            if (c < 2) CST(7);
            if (c == 0) fence_async_smem();
            wgmma_fence();
#pragma unroll
            for (int m = 0; m < 8; m++) {
                wgmma_rs128(acc, f[m][0], f[m][1], db - (uint64_t)(2 * m), m);
                if (m == CV_HAND && c < 4) asm volatile("bar.arrive %0, 256;" ::"r"(5 - wgu) : "memory");
            }
            wgmma_commit();
            asm volatile("griddepcontrol.launch_dependents;" ::: "memory");
            TSTAMPC(2 + 3 * c); CST(13 + (c >> 1));
            meanwhile();
            wgmma_wait<0>();
            TSTAMPC(3 + 3 * c); CST(10 + (c >> 1));
            uint32_t w[16];
#pragma unroll
            for (int j = 0; j < 16; j++) w[j] = j ? pack2(acc[4 * j] + acc[4 * j - 2], acc[4 * j + 1] + acc[4 * j - 1]) : pack2(acc[0], acc[1]);
#pragma unroll
            for (int j = 0; j < 16; j += 4) stsm_x4_t(ya + 256 * j, w[j], w[j + 1], w[j + 2], w[j + 3]);
            __syncwarp();
            if (lane == 0) mbar_arrive(cnt + 8 * c);
            c += 2; ya += 16384; db += ULEN / 4;
        };
        const uint32_t e4 = lc.e4, e8 = e4 + 428 - 4 * g;
        uint2 fl[4];
        uint32_t kk;
#pragma unroll 1
        for (;;) {
            if (c != 1) chain(fa, [&] {
                if (c == 3 || warp + c == 12) {
#pragma unroll
                    for (int k = 0; k < 19; k++) (k < 16 ? fn[(k >> 1) & 7][k & 1] : fl[k & 3]) = make_uint2(lds1(k < 10 ? e4 + 32 * k + 16 : e8 + 32 * k - 304), lds1(k < 10 ? e4 + 32 * k : e8 + 32 * k - 320));
                    fl[3] = make_uint2(lds1(lc.en), lds1(lc.en - 32));
                    kk = lds1(smem_u32(sm + CV_SM_T) + TAPB * hc + TAPE + 1672);
                }
            });
            if (c > 4) break;
            if (c == 2) { asm volatile("bar.sync 7, 384;" ::: "memory"); fence_async_smem(); }
            chain(fn, [&] { if (c == 2) near_taps(fa, 4); });
        }
        TSTAMP1X(6, 256); CST(2);
        if (wgu || warp == 8) {
            constexpr int seq[29] = {5, 6, 32, 7, 33, 8, 34, 9, 35, 10, 36, 11, 12, 13, 14, 15, 16, 17, 37, 18, 38, 19, 20, 21, 39, 22, 40, 23, 24};
            uint2 f[20];
#pragma unroll
            for (int k = 0; k < 20; k++) f[k] = k < 16 ? fn[(k >> 1) & 7][k & 1] : fl[k & 3];
            far(Int<10>(), seq, lc, hc, lane, f, kk);
        }
    } else {
        asm volatile("setmaxnreg.dec.sync.aligned.u32 88;");
        CV_IDX
        CST(5);
        const uint4* ppv = piv + tid;
        const float4* psv = sum + tid;
        const uint2* pxv = reinterpret_cast<const uint2*>(x1T + (size_t)d0 * XCP) + (tid >> 4) * 32 + (tid & 15);
        asm volatile("st.shared.u64 [%0], %1;" ::"r"(smem_u32(sm + CV_SM_O) + tid * 16), "l"((uint64_t)ppv ^ (uint64_t)psv ^ (uint64_t)pxv) : "memory");
        const int tc = (0x04302100 >> (4 * warp)) & 7;
        const Lc lc = lane_consts(lane, tc);
        pdl_sync();
        SPAN(3 + 4 * layer, 1);
        TSTAMP(0); CST(0);
        if (tid == 0) TSTAMPC(0);
        if (threadIdx.x == 0) { GSTAMP(g_tim, 15); }
        float4 sv[4];
        uint4 pv;
#pragma unroll
        for (int k = 0; k < 4; k++)
            asm volatile(CV_LD ".v4.f32 {%0,%1,%2,%3}, [%4];" : "=f"(sv[k].x), "=f"(sv[k].y), "=f"(sv[k].z), "=f"(sv[k].w) : "l"(psv + 256 * k) : "memory");
        asm volatile(CV_LD ".v4.u32 {%0,%1,%2,%3}, [%4];" : "=r"(pv.x), "=r"(pv.y), "=r"(pv.z), "=r"(pv.w) : "l"(ppv) : "memory");
        uint2 xe[CV_CPB], xo[CV_CPB];
#pragma unroll
        for (int c = 0; c < CV_NL; c++) {
            asm volatile(CV_LD ".v2.u32 {%0,%1}, [%2];" : "=r"(xe[c].x), "=r"(xe[c].y) : "l"(pxv + c * (XCP / 4)) : "memory");
            asm volatile(CV_LD ".v2.u32 {%0,%1}, [%2];" : "=r"(xo[c].x), "=r"(xo[c].y) : "l"(pxv + c * (XCP / 4) + 16) : "memory");
        }
#define CV_XD 300
#define CV_XW 0
        if (warp == CV_XW) {
            if (elect()) {
                const uint32_t c0 = clock();
                mbar_init(cnt + 56, 1);
                asm volatile("fence.mbarrier_init.release.cluster;" ::: "memory");
                mbar_expect_tx(cnt + 56, CV_CPB * 4096);
                while (clock() - c0 < CV_XD) ;
#pragma unroll
                for (int c = CV_NL; c < CV_CPB + CV_NL; c++) bulk_load(smem_u32(Xs + (c % CV_CPB) * XLEN), x1T + (size_t)(d0 + c % CV_CPB) * XCP, 4096, cnt + 56);
            }
            __syncwarp();
            CST(15);
        }
        constexpr float idm = 1.0f / DM;
        uint32_t mw[4];
        float rs[8];
#pragma unroll
        for (int k = 0; k < 4; k++) {
            const uint32_t pw = k == 0 ? pv.x : k == 1 ? pv.y : k == 2 ? pv.z : pv.w;
            mw[k] = pack2(fmaf(sv[k].x, idm, __uint_as_float(pw << 16)), fmaf(sv[k].z, idm, __uint_as_float(pw & 0xffff0000u)));
            uint32_t vr;
            asm("cvt.rn.relu.bf16x2.f32 %0, %1, %2;" : "=r"(vr) : "f"(fmaf(sv[k].z * -idm, sv[k].z, sv[k].w) * idm), "f"(fmaf(sv[k].x * -idm, sv[k].x, sv[k].y) * idm));
            const uint32_t ve = pack2(__uint_as_float(vr << 16) + 1e-5f, __uint_as_float(vr & 0xffff0000u) + 1e-5f);
            const uint32_t sd = pack2(sqrt_apx(__uint_as_float(ve << 16)), sqrt_apx(__uint_as_float(ve & 0xffff0000u)));
            rs[2 * k] = rcp_apx(__uint_as_float(sd << 16)); rs[2 * k + 1] = rcp_apx(__uint_as_float(sd & 0xffff0000u));
        }
        if (rs[0] != 123.f) TSTAMP(13);
        const uint32_t ua = smem_u32(Us) + usw(tid + UPADF / 8) * 16;
        uint32_t uw[CV_CPB][4];
#pragma unroll
        for (int c = 0; c < CV_CPB; c++) {
            if (c == CV_NL) {
                if (warp == CV_XW) { mbar_wait(cnt + 56, 0); CST(7); }
                asm volatile("bar.sync 10, 256;" ::: "memory");
            }
            if (c == 1 || c == 2) {
#pragma unroll
                for (int k = c; k < (c == 1 ? 2 : CV_CPB); k++) {
 const uint4 v = ldx(smem_u32(Xs + k * XLEN) + (tid >> 4) * 256 + (tid & 15) * 8); xe[k] = make_uint2(v.x, v.y); xo[k] = make_uint2(v.z, v.w); }
            }
            const uint32_t e0 = sub2(xe[c].x, mw[0]), e1 = sub2(xe[c].y, mw[1]), o0 = sub2(xo[c].x, mw[2]), o1 = sub2(xo[c].y, mw[3]);
            uw[c][0] = pack2(__uint_as_float(e0 << 16) * rs[0], __uint_as_float(o0 << 16) * rs[4]); uw[c][1] = pack2(__uint_as_float(e0 & 0xffff0000u) * rs[1], __uint_as_float(o0 & 0xffff0000u) * rs[5]);
            uw[c][2] = pack2(__uint_as_float(e1 << 16) * rs[2], __uint_as_float(o1 << 16) * rs[6]); uw[c][3] = pack2(__uint_as_float(e1 & 0xffff0000u) * rs[3], __uint_as_float(o1 & 0xffff0000u) * rs[7]);
            asm volatile("st.shared.v4.u32 [%0], {%1,%2,%3,%4};" ::"r"(ua + c * ULEN * 2), "r"(uw[c][0]), "r"(uw[c][1]), "r"(uw[c][2]), "r"(uw[c][3]) : "memory");
            if (c < 2) {
                asm volatile("bar.arrive %0, 384;" ::"r"(2 + 4 * c) : "memory");
                if (layer > 29 - c) __trap();
                CST(11 + c);
            }
        }
        asm volatile("bar.arrive 7, 384;" ::: "memory");
        asm volatile("bar.sync 3, 512;" ::: "memory");
        TSTAMP(1); CST(1);
        {
            auto box = [&](auto c0, auto c1, int chunk, int cb, bool full) {
                const uint32_t ea = smem_u32(Us + cb * ULEN) + usw(chunk + UPADF / 8 + (lane ? 1 : -1)) * 16, bx = smem_u32(sm + CV_SM_B + cb * BX_LEN) + chunk * 16;
                uint32_t lo[CV_CPB][4], hi[CV_CPB][2];
#pragma unroll
                for (int c = c0; c < c1; c++) {
                    lo[c][0] = 0;
#pragma unroll
                    for (int k = 1; k < 4; k++) lo[c][k] = __shfl_up_sync(~0u, uw[c][k], 1);
#pragma unroll
                    for (int k = 0; k < 2; k++) hi[c][k] = __shfl_down_sync(~0u, uw[c][k], 1);
                }
#pragma unroll
                for (int c = c0; c < c1; c++)
                    asm volatile("{\n.reg .pred p, q;\nsetp.eq.s32 p, %7, 0;\nsetp.eq.s32 q, %7, 31;\n@p ld.shared.v4.u32 {%0,%1,%2,%3}, [%6];\n@q ld.shared.v2.u32 {%4,%5}, [%6];\n}"
                                 : "+r"(lo[c][0]), "+r"(lo[c][1]), "+r"(lo[c][2]), "+r"(lo[c][3]), "+r"(hi[c][0]), "+r"(hi[c][1]) : "r"(ea + c * ULEN * 2), "r"(lane) : "memory");
#pragma unroll
                for (int c = c0; c < c1; c++) {
                    const uint32_t e[9] = {lo[c][1], lo[c][2], lo[c][3], uw[c][0], uw[c][1], uw[c][2], uw[c][3], hi[c][0], hi[c][1]};
                    uint32_t o[8], p[8], t[7], b3[5], b5[7];
#pragma unroll
                    for (int i = 0; i < 8; i++) { o[i] = __byte_perm(e[i], e[i + 1], 0x5432); p[i] = add2(e[i], o[i]); }
#pragma unroll
                    for (int i = 0; i < 5; i++) b3[i] = add2(o[i], p[i + 1]);
                    sts4(bx + c * BX_LEN + BX_3 + 160, b3);
#pragma unroll
                    for (int i = 1; i < 7; i++) { t[i] = add2(p[i], p[i + 1]); b5[i] = add2(t[i], e[i + 2]); }
                    sts4(bx + c * BX_LEN + BX_5 + 160, b5 + 2);
                    if (full) {
#pragma unroll
                        for (int i = 1; i < 5; i++) { b3[i] = add2(b3[i], t[i + 2]); t[i] = add2(t[i], b5[i + 2]); }
                        sts4(bx + c * BX_LEN + BX_7 + 272, b3 + 1);
                        sts4(bx + c * BX_LEN + BX_9 + 272, t + 1);
                    }
                }
            };
            auto reload = [&](int c, uint32_t a) { const uint4 v = lds4(a); uw[c][0] = v.x; uw[c][1] = v.y; uw[c][2] = v.z; uw[c][3] = v.w; };
            if (warp >= 6) {
#pragma unroll
                for (int c = 0; c < 3; c++) reload(c, ua - 1024 + (c + 2) * ULEN * 2);
            }
            if (warp >= 4) {
#pragma unroll
                for (int c = 3; c < 5; c++) reload(c, ua - 2048 + c * ULEN * 2);
            }
            box(Int<0>(), Int<3>(), warp < 6 ? tid : tid - 64, warp < 6 ? 0 : 2, warp < 4);
            if (warp >= 4) box(Int<3>(), Int<5>(), tid - 128, 0, true);
            else if (tid >= 128 - CV_CPB) {
                const int c = 127 - tid;
                const uint2 v = *reinterpret_cast<const uint2*>(Us + c * ULEN + UPADF);
                const float s1 = __uint_as_float(v.x << 16), s2 = s1 + __uint_as_float(v.x & 0xffff0000u), s3 = s2 + __uint_as_float(v.y << 16), s4 = s3 + __uint_as_float(v.y & 0xffff0000u);
                unsigned char* bc = sm + CV_SM_B + c * BX_LEN;
                *reinterpret_cast<uint32_t*>(bc + BX_5 + 156) = pack2(s1, s2);
                *reinterpret_cast<uint2*>(bc + BX_7 + 264) = make_uint2(v.x << 16, pack2(s2, s3));
                *reinterpret_cast<uint2*>(bc + BX_9 + 264) = make_uint2(pack2(s1, s2), pack2(s3, s4));
            }
        }
        __syncwarp();
        if (lane == 0) mbar_arrive(cnt + 40);
        TSTAMP(2); CST(2);
        if (layer && blockIdx.x == 0 && tid == 224) g_epoch = ld_epoch();
        __syncwarp();
        if ((0x6e >> warp) & 1) {
            constexpr int seq[16] = {0, 1, 2, 3, 4, 5, 6, 32, 7, 8, 9, 33, 10, 34, 11, 12};
            uint2 f[20];
            mbar_wait(cnt, 0);
            const uint32_t e8 = lc.e4 + 428 - (lane & 28);
#pragma unroll
            for (int k = 0; k < 13; k++) f[k] = make_uint2(lds1(k < 10 ? lc.e4 + 32 * k + 16 : e8 + 32 * k - 304), lds1(k < 10 ? lc.e4 + 32 * k : e8 + 32 * k - 320));
            f[19] = make_uint2(lds1(lc.en), lds1(lc.en - 32));
            far(Int<4>(), seq, lc, tc, lane, f, lds1(smem_u32(sm + CV_SM_T) + TAPB * tc + TAPE + 1672));
        }
    }
    {
        CV_IDX
        if ((0xc91 >> warp) & 1) {
            const int c = __popc(0xc91 & ((1 << warp) - 1));
            uint4 xv[2], yv[2];
#pragma unroll
            for (int k = 0; k < 2; k++) xv[k] = ldx(smem_u32(Xs + c * XLEN) + 512 * k + (lane >> 4) * 256 + (lane & 15) * 8);
            const uint32_t u0 = lds1(smem_u32(Us + c * ULEN) + (lane == 31 ? UPADF * 2 : 0));
            mbar_wait(cnt + 8 * c, 0);
#pragma unroll
            for (int k = 0; k < 2; k++) yv[k] = lds4(smem_u32(sm + CV_SM_Y) + c * 8192 + 512 * k + usw(lane) * 16);
            const uint4 yz = lds4(smem_u32(sm + CV_SM_Y) + c * 8192 + 4096 + usw(lane) * 16);
            const float kk = __uint_as_float(lds1(smem_u32(sm + CV_SM_T) + TAPB * c + TAPE + 1272) << 16);
            yv[1].x = add2(yv[1].x, yz.x); yv[1].y = add2(yv[1].y, yz.y); yv[1].z = add2(yv[1].z, yz.z);
            yv[1].w = pack2(fmaf(kk, __uint_as_float(u0 << 16), __uint_as_float(yv[1].w << 16) + __uint_as_float(yz.w << 16)),
                            fmaf(kk, __uint_as_float(u0 << 16) + __uint_as_float(u0 & 0xffff0000u), __uint_as_float(yv[1].w & 0xffff0000u) + __uint_as_float(yz.w & 0xffff0000u)));
#pragma unroll
            for (int k = 0; k < 2; k++) cv_store(dq + c * XCP * 2 + (lane >> 4) * 256 + (lane & 15) * 8 + 512 * k, xv[k], yv[k]);
        }
        TSTAMP(4); CST(8);
        if (layer == 1) {
            const int rb = (blockIdx.x >> 3) + (warp & 8) * 2, cg = blockIdx.x & 7, ch = (tid >> 3) & 31;
            const bf16* src = dst + (size_t)(cg * 80 + ch) * XCP + rb * 64 + (tid & 7) * 8;
            uint32_t v[3][4];
            __syncthreads();
            if (warp & 8) { const uint32_t c0 = clock(); while (clock() - c0 < 300) ; }
            uint32_t todo = (warp & 4) ? 3 : 7;
#pragma unroll 1
            for (int it = 0; it < SPIN_MAX; it++) {
#pragma unroll
                for (int k = 0; k < 3; k++)
                    if (todo >> k & 1)
                        asm volatile("ld.relaxed.gpu.global.v4.u32 {%0,%1,%2,%3}, [%4];" : "=r"(v[k][0]), "=r"(v[k][1]), "=r"(v[k][2]), "=r"(v[k][3]) : "l"(src + k * (32 * XCP)) : "memory");
#pragma unroll
                for (int k = 0; k < 3; k++)
                    if ((todo >> k & 1) && v[k][0] != ~0u && v[k][1] != ~0u && v[k][2] != ~0u && v[k][3] != ~0u) {
                        *reinterpret_cast<uint4*>(sm + (32 * k + ch) * 272 + ((tid & 7) + (warp & 8)) * 16) = make_uint4(v[k][0], v[k][1], v[k][2], v[k][3]);
                        todo ^= 1u << k;
                    }
                if (!todo) break;
                __nanosleep(CV_SLEEP);
            }
            __syncwarp();
            asm volatile("bar.sync %0, 256;" ::"r"(8 + (warp >> 3)) : "memory");
            uint32_t w[12];
#pragma unroll
            for (int k = 0; k < 3; k++) ldsm_x4(&w[4 * k], smem_u32(sm) + min(32 * k + lane, 79) * 272 + warp * 16);
            const uint32_t ot = smem_u32(sm + CV_SM_O) + warp * 1280, oa = ot + (lane & 7) * 160 + (lane >> 3) * 16;
            stsm_x4_t(oa, w[0], w[1], w[2], w[3]);
            stsm_x4_t(oa + 64, w[4], w[5], w[6], w[7]);
            asm volatile("stmatrix.sync.aligned.m8n8.x2.trans.shared.b16 [%0], {%1,%2};" ::"r"(oa + 128), "r"(w[8]), "r"(w[9]) : "memory");
            fence_async_smem();
            __syncwarp();
            if (lane == 0) {
                asm volatile("cp.async.bulk.tensor.3d.global.shared::cta.bulk_group [%0, {%1, %2, %3}], [%4];" ::"l"(&tmOut), "r"(cg * 80), "r"((rb >> 1) * 64 + 8 * (warp & 7)), "r"(rb & 1), "r"(ot) : "memory");
                asm volatile("cp.async.bulk.commit_group;" ::: "memory");
                asm volatile("cp.async.bulk.wait_group.read 0;" ::: "memory");
            }
        }
    }
    TSTAMP(3); CST(9); CST_END;
    GSTAMP(g_tim, 14);
    SPAN(3 + 4 * layer, 3);
}

template <int TA, int TB>
__device__ __forceinline__ void wgmma_n240(float (&d)[120], uint64_t da, uint64_t db, int acc) {
    asm volatile("{\n.reg .pred p;\nsetp.ne.b32 p, %124, 0;\nwgmma.mma_async.sync.aligned.m64n240k16.f32.bf16.bf16 {%0,%1,%2,%3,%4,%5,%6,%7,%8,%9,%10,%11,%12,%13,%14,%15,%16,%17,%18,%19,%20,%21,%22,%23,%24,%25,%26,%27,%28,%29,%30,%31,%32,%33,%34,%35,%36,%37,%38,%39,%40,%41,%42,%43,%44,%45,%46,%47,%48,%49,%50,%51,%52,%53,%54,%55,%56,%57,%58,%59,%60,%61,%62,%63,%64,%65,%66,%67,%68,%69,%70,%71,%72,%73,%74,%75,%76,%77,%78,%79,%80,%81,%82,%83,%84,%85,%86,%87,%88,%89,%90,%91,%92,%93,%94,%95,%96,%97,%98,%99,%100,%101,%102,%103,%104,%105,%106,%107,%108,%109,%110,%111,%112,%113,%114,%115,%116,%117,%118,%119}, %120, %121, p, 1, 1, %122, %123;\n}"
                 : "+f"(d[0]), "+f"(d[1]), "+f"(d[2]), "+f"(d[3]), "+f"(d[4]), "+f"(d[5]), "+f"(d[6]), "+f"(d[7]), "+f"(d[8]), "+f"(d[9]), "+f"(d[10]), "+f"(d[11]), "+f"(d[12]), "+f"(d[13]), "+f"(d[14]), "+f"(d[15]), "+f"(d[16]), "+f"(d[17]), "+f"(d[18]), "+f"(d[19]), "+f"(d[20]), "+f"(d[21]), "+f"(d[22]), "+f"(d[23]), "+f"(d[24]), "+f"(d[25]), "+f"(d[26]), "+f"(d[27]), "+f"(d[28]), "+f"(d[29]), "+f"(d[30]), "+f"(d[31]), "+f"(d[32]), "+f"(d[33]), "+f"(d[34]), "+f"(d[35]), "+f"(d[36]), "+f"(d[37]), "+f"(d[38]), "+f"(d[39]), "+f"(d[40]), "+f"(d[41]), "+f"(d[42]), "+f"(d[43]), "+f"(d[44]), "+f"(d[45]), "+f"(d[46]), "+f"(d[47]), "+f"(d[48]), "+f"(d[49]), "+f"(d[50]), "+f"(d[51]), "+f"(d[52]), "+f"(d[53]), "+f"(d[54]), "+f"(d[55]), "+f"(d[56]), "+f"(d[57]), "+f"(d[58]), "+f"(d[59]), "+f"(d[60]), "+f"(d[61]), "+f"(d[62]), "+f"(d[63]), "+f"(d[64]), "+f"(d[65]), "+f"(d[66]), "+f"(d[67]), "+f"(d[68]), "+f"(d[69]), "+f"(d[70]), "+f"(d[71]), "+f"(d[72]), "+f"(d[73]), "+f"(d[74]), "+f"(d[75]), "+f"(d[76]), "+f"(d[77]), "+f"(d[78]), "+f"(d[79]), "+f"(d[80]), "+f"(d[81]), "+f"(d[82]), "+f"(d[83]), "+f"(d[84]), "+f"(d[85]), "+f"(d[86]), "+f"(d[87]), "+f"(d[88]), "+f"(d[89]), "+f"(d[90]), "+f"(d[91]), "+f"(d[92]), "+f"(d[93]), "+f"(d[94]), "+f"(d[95]), "+f"(d[96]), "+f"(d[97]), "+f"(d[98]), "+f"(d[99]), "+f"(d[100]), "+f"(d[101]), "+f"(d[102]), "+f"(d[103]), "+f"(d[104]), "+f"(d[105]), "+f"(d[106]), "+f"(d[107]), "+f"(d[108]), "+f"(d[109]), "+f"(d[110]), "+f"(d[111]), "+f"(d[112]), "+f"(d[113]), "+f"(d[114]), "+f"(d[115]), "+f"(d[116]), "+f"(d[117]), "+f"(d[118]), "+f"(d[119])
                 : "l"(da), "l"(db), "n"(TA), "n"(TB), "r"(acc));
}

__device__ __forceinline__ void wgmma_n80(float (&d)[40], uint64_t da, uint64_t db, int acc) {
    asm volatile("{\n.reg .pred p;\nsetp.ne.b32 p, %42, 0;\nwgmma.mma_async.sync.aligned.m64n80k16.f32.bf16.bf16 {%0,%1,%2,%3,%4,%5,%6,%7,%8,%9,%10,%11,%12,%13,%14,%15,%16,%17,%18,%19,%20,%21,%22,%23,%24,%25,%26,%27,%28,%29,%30,%31,%32,%33,%34,%35,%36,%37,%38,%39}, %40, %41, p, 1, 1, 0, 1;\n}"
                 : "+f"(d[0]), "+f"(d[1]), "+f"(d[2]), "+f"(d[3]), "+f"(d[4]), "+f"(d[5]), "+f"(d[6]), "+f"(d[7]), "+f"(d[8]), "+f"(d[9]), "+f"(d[10]), "+f"(d[11]), "+f"(d[12]), "+f"(d[13]), "+f"(d[14]), "+f"(d[15]), "+f"(d[16]), "+f"(d[17]), "+f"(d[18]), "+f"(d[19]), "+f"(d[20]), "+f"(d[21]), "+f"(d[22]), "+f"(d[23]), "+f"(d[24]), "+f"(d[25]), "+f"(d[26]), "+f"(d[27]), "+f"(d[28]), "+f"(d[29]), "+f"(d[30]), "+f"(d[31]), "+f"(d[32]), "+f"(d[33]), "+f"(d[34]), "+f"(d[35]), "+f"(d[36]), "+f"(d[37]), "+f"(d[38]), "+f"(d[39])
                 : "l"(da), "l"(db), "r"(acc));
}

constexpr int A1_THREADS = 384;
constexpr int A1_NST = 4;
#define A1_SKEW 8
constexpr int A1_STAGE = 16384 + WQ_STAGE;
constexpr int A1_KVP = 336;
constexpr int A1_SM_KV = 2 * A1_STAGE;
constexpr int A1_SM_END = A1_NST * A1_STAGE;
constexpr int A1_SM_BAR = A1_SM_END + 3072 + 3 * WOB + 64;
constexpr int A1_SM_RS = A1_SM_END + 512;
constexpr int A1_SM_W0 = A1_SM_END + 3072, A1_SM_W3 = A1_SM_END - 3 * WOB, A1_SM_A1 = 2 * WOB, A1_SM_A0 = A1_SM_A1 + 61440;
constexpr int A1_SM_XA = A1_SM_W0 + 2 * WOB, A1_SM_XB = A1_SM_XA + 2048;
constexpr int A1_SMEM = A1_SM_BAR + 512 + 7 * CST_EXTRA / 4;
static_assert(A1_SM_W3 >= A1_SM_KV + 144 * A1_KVP && A1_SM_W3 % 512 == 0 && A1_SM_A1 % 1024 == 0 && A1_SM_A0 <= A1_SM_KV && A1_SM_A0 + 61440 <= A1_SM_W3 && A1_SMEM <= 232448 && 11 * 4096 <= A1_STAGE, "layout");
__device__ __forceinline__ constexpr uint32_t wo_off(int h) { return h * WOB + (h < 3 ? A1_SM_W0 : h < 6 ? A1_SM_W3 - 3 * WOB : -6 * WOB); }
#define A1_FRED "red.relaxed.gpu.global.add.u32"
#define A1_FLD "ld.acquire.gpu.global.u32"
#define ST_SLEEP 20
#define ST_SLEEP0 300
#define WO_LATE bar_done
#define A1_P0 2
#define A1_PW (kb - 2)
#define A1_FSPIN SPIN_MAX
#define A1_FSLEEP 40
#define YT_LAYER 1
#define WOT 352
#define A1_WOAT 6

template <int L>
__device__ __forceinline__ void a1_mainloop(float (&acc)[120], uint32_t sbase, uint32_t bars, int wg, int tile) {
    constexpr int layer = L; (void)layer;
    const uint64_t da0 = L ? make_desc(sbase + wg * 8192, 8192, 1024, 1) : make_desc(sbase + wg * 8192, 16, 1024, 1), db0 = make_desc(sbase + 16384, 1024, 256, 3);
#pragma unroll 1
    for (int t = 0;; t++) {
        const int st = t % A1_NST;
        mbar_wait(bars + 8 * st, (t / A1_NST) & 1);
        if (t == A1_SKEW && wg == 0) mbar_wait(bars + 160, 0);
        TSTAMP3(1 + t);
        if (t == 0) CSA(0);
        wgmma_fence();
#pragma unroll
        for (int kk = 0; kk < 4; kk++) wgmma_n240<L, 1>(acc, da0 + (uint32_t)(st * (A1_STAGE / 16) + kk * (L ? 128 : 2)), db0 + (uint32_t)(st * (A1_STAGE / 16) + (kk >> 1) * (WQ_STAGE / 32) + (kk & 1) * 32), kk ? 1 : t);
        wgmma_commit();
        if (t == 9) break;
        if (t == A1_SKEW - 1 && wg == 0) wgmma_wait<0>(); else wgmma_wait<1>();
        if (t > 0 && (threadIdx.x & 127) == 0) {
            if (t != A1_SKEW || wg) mbar_arrive(bars + 8 * (A1_NST + (t - 1) % A1_NST));
            if (t == A1_SKEW - 1 && wg == 0) mbar_arrive(bars + 8 * (A1_NST + t % A1_NST));
        }
    }
}

template <bool MAP>
__global__ void __launch_bounds__(A1_THREADS, 1) a1_kernel(const __grid_constant__ Par in, const __grid_constant__ CUtensorMap tmX, const __grid_constant__ CUtensorMap tmR,
                                                           const __grid_constant__ CUtensorMap tmX1, const __grid_constant__ KgMaps tmW, const __grid_constant__ TileTab tab) {
#define layer in.layer
    const unsigned char* const wo = reinterpret_cast<const unsigned char*>(in.wop);
    float2* const rsum = reinterpret_cast<float2*>(in.sum);
    uint4* const of = in.of;
    extern __shared__ __align__(1024) unsigned char stg[];
    const uint32_t sbase = smem_u32(stg);
    const uint32_t bars = sbase + A1_SM_BAR;
    const uint32_t bar_stat = bars + 64, bar_kv = bars + 72, bar_rd = bars + 168;
    const uint32_t bar_wo = bars + 208, bar_done = bars + 216, bar_pv = bars + 224, bar_kvf = bars + 232, bar_f2 = bars + 248, bar_e2 = bars + 384, que = bars + 448;
    const int tid = threadIdx.x;
    CSK(0);
    const int w = __shfl_sync(~0u, tid >> 5, 0), wg = w >> 2;
    uint32_t smid;
    asm volatile("mov.u32 %0, %smid;" : "=r"(smid));
    const uint4 tv = tab.e[(MAP ? smid : blockIdx.x) + (tid & (smid >> 12))];
    const uint64_t pa = reinterpret_cast<const uint64_t*>(&in)[tid & (smid >> 12)], pb = reinterpret_cast<const uint64_t*>(&in)[6 + (tid & (smid >> 12))];
    const bool one = elect();
    uint32_t tz;
    const unsigned char* wq;
    auto entry = [&] { tz = __shfl_sync(~0u, tv.z, 0); wq = (const unsigned char*)(((uint64_t)__shfl_sync(~0u, tv.y, 0) << 32) | __shfl_sync(~0u, tv.x, 0)); };
    auto issue_w = [&](unsigned it) { bulk_load(sbase + (it % A1_NST) * A1_STAGE + 16384, wq + it * WQ_STAGE, WQ_STAGE, bars + 8 * (it % A1_NST)); };
    auto issue_x = [&](unsigned it, int kb) {
        asm volatile("cp.async.bulk.tensor.5d.shared::cluster.global.mbarrier::complete_tx::bytes [%0], [%1, {%3, %3, %3, %4, %5}], [%2];"
                     ::"r"(sbase + (it % A1_NST) * A1_STAGE), "l"(&tmX), "r"(bars + 8 * (it % A1_NST)), "r"(0), "r"(tz & 15), "r"(kb) : "memory");
    };
    auto first_x = [&] {
        issue_x(0, (tz >> 16) & 7); issue_x(1, ((tz >> 16) & 7) + 1);
    };
    auto expect = [&] {
#pragma unroll
        for (int i = 0; i < A1_NST; i++) mbar_expect_tx(bars + 8 * i, A1_STAGE);
    };
    if (w == 8) {
        if (one) {
            prefetch_tmap(&tmX); prefetch_tmap(&tmW.q);
#pragma unroll
            for (int i = 0; i < A1_NST; i++) mbar_init(bars + 8 * i, 1);
            asm volatile("fence.mbarrier_init.release.cluster;" ::: "memory");
        }
        __syncwarp();
        asm volatile("bar.arrive 0, 384;" ::: "memory");
        if (smid >> 12) __trap();
        entry();
        if ((tz & 0x80000010u) == 16) {
            if (one) {
                issue_w(0);
                asm volatile("griddepcontrol.wait;" ::: "memory");
                first_x();
                issue_w(1);
                expect();
                asm volatile("griddepcontrol.launch_dependents;" ::: "memory");
            }
#pragma unroll
            for (int kb = 2; kb < A1_NST; kb++) {
                __syncwarp();
                mbar_wait(bars + 8 * (kb - 2), 0);
                if (one) { issue_x(kb, ((tz >> 16) & 7) + kb); issue_w(kb); }
                CSK(6 + kb);
            }
        }
        __syncwarp();
        if (!(tz & 16) && blockIdx.x < 128) kgen_first(in, tmW, sbase + A1_SM_W0, bars - 24, one);
        __syncwarp();
    }
    if (w > 8) CSK(8);
    const bool gen = w != 8 && in.logA && blockIdx.x < 128;
    KgPar kp;
    const int w11 = w < 8 ? 2 * (w & 3) + (w >> 2) : w - 1;
    if (gen) kgen_load(in, reinterpret_cast<const bf16*>(pa), w11, kp);
    if (w > 8) CSK(9);
    if (w == 8) {
        const int tile = tz >> 24, mb = tz & 15, hg = (tz >> 8) & 7, kb0 = (tz >> 16) & 7;
        const unsigned l1 = (tz >> 4) & 1;
        if (__builtin_expect(!l1, 0)) {
            CSK(1);
            const uint32_t ep = ld_epoch();
            if (one) {
                kgen_side(in, sbase + A1_SM_W0, bars - 24);
                if (tile < 128) { first_x(); issue_x(2, kb0 + 2); expect(); }
                asm volatile("cp.async.bulk.wait_group 0;" ::: "memory");
            }
            __syncwarp();
            asm volatile("bar.arrive 10, 96;" ::: "memory");
            CSK(6);
            if (tile < 128) {
                await_all(96 + 32 * hg, ep * 15);
#define KG_PACE 1
                if (one) { issue_w(0); if (KG_PACE > 1) issue_w(1); if (KG_PACE > 2) issue_w(2); }
                if (KG_PACE < 3) {
                    __syncwarp();
                    mbar_wait(bars, 0);
                    if (one && KG_PACE < 2) issue_w(1);
                    if (KG_PACE == 0) { __syncwarp(); mbar_wait(bars + 8, 0); }
                    if (one) issue_w(2);
                }
            }
            CSK(7);
            asm volatile("bar.sync 3, 384;" ::: "memory");
            if (tile < 128 && one) {
                fence_async_smem();
                issue_x(3, kb0 + 3); issue_w(3);
                mbar_expect_tx(bars + 240, 20480);
                bulk_load(sbase + A1_SM_W0, in.x + (size_t)(mb * 128 + hg * 16) * DM, 20480, bars + 240);
            }
            __syncwarp();
            CSK(9);
        } else asm volatile("bar.sync 3, 64;" ::: "memory");
        if (tile < 128 && elect()) {
#pragma unroll 1
            for (unsigned kb = A1_NST; kb < 10; kb++) {
                mbar_wait(bars + 8 * (A1_NST + kb % A1_NST), ((kb / A1_NST) - 1) & 1);
                if (l1 && kb < 9) mbar_wait(bar_rd + 8 * (kb - A1_NST), 0);
                mbar_expect_tx(bars + 8 * (kb % A1_NST), A1_STAGE);
                issue_x(kb, kb < 5 ? kb + kb0 : kb - kb0); issue_w(kb);
                if (kb == (l1 ? A1_WOAT : 9)) {
                    if (!l1) { mbar_wait(bar_stat, 0); asm volatile("fence.proxy.async.global;" ::: "memory"); }
                    mbar_expect_tx(bar_wo, 8 * WOB);
                    bulk_load(sbase + A1_SM_W0, wo + hg * 8 * WOB, 2 * WOB, bar_wo);
                }
            }
            mbar_wait(bars + 8 * (A1_NST + 3), 1);
            bulk_load(sbase + A1_SM_W3, wo + (hg * 8 + 3) * WOB, 3 * WOB, bar_wo);
        }
        CSA(4); CSA_END;
        return;
    }
    {
        if (w < 8 && one) {
#pragma unroll 1
            for (uint32_t c = (w & 4 ? w & 2 ? 0x1111112'01111111ull : 0x1111111'01111184ull : w & 2 ? 0x3122222'01111111ull : 0x1111132'02220000ull) >> (32 * (w & 1)), b = bars + 56 * w; c; c >>= 4, b += 8)
                if (c & 15) mbar_init(b, c & 15);
            asm volatile("fence.mbarrier_init.release.cluster;" ::: "memory");
        }
        __syncwarp();
        asm volatile("bar.sync 0, 384;" ::: "memory");
        if (layer) {
            if (w == 9) asm volatile("bar.arrive 3, 64;" ::: "memory");
        } else {
            if (gen) { SPAN(0, 0); SPAN(0, 1); kgen_tables(in, reinterpret_cast<uint4*>(stg + 3 * A1_STAGE), w11, kp); }
            else if (w != 11 && w11 > 1) asm volatile("bar.arrive 9, 352;" ::: "memory");
            __syncwarp();
            if (w11 < 2) {
                asm volatile("bar.sync 10, 96;" ::: "memory");
                kgen_sums(in, sbase + A1_SM_W0, w11);
                __syncwarp();
                asm volatile("bar.arrive 9, 352;" ::: "memory");
                CSK(1);
            }
            if (w == 9) asm volatile("bar.sync 3, 384;" ::: "memory"); else asm volatile("bar.arrive 3, 384;" ::: "memory");
        }
    }
    tz = __shfl_sync(~0u, tv.z + (uint32_t)(pb >> 32), 0);
    const int tile = tz >> 24, mb = tz & 15, hg = (tz >> 8) & 7;
    float2* rst = reinterpret_cast<float2*>(stg + A1_SM_RS) + 8;
    if (wg == 2) {
        if (w == 11 && layer == 0) {
            asm volatile("bar.sync 9, 352;" ::: "memory");
            CSK(5);
            if (one) publish(64);
            __syncwarp();
            CSK(6);
        }
        if (tile >= 128) { sm_idle(layer); return; }
        if (w == 10) {
            if (one) { prefetch_tmap(&tmR); prefetch_tmap(&tmX1); }
            uint32_t ns;
            asm volatile("mov.u32 %0, %nsmid;" : "=r"(ns));
            if (MAP && ns != 132) __trap();
        }
        __syncwarp();
        if (w == 9) {
            if (layer && one) {
                mbar_expect_tx(bar_stat, 3840);
                bulk_load(sbase + A1_SM_XB, g_xb + tile * 240, 3840, bar_stat);
            }
            __syncwarp();
            uint4* pre = of + (mb * 8 + hg) * 1280 + (tid - 288);
#pragma unroll 1
            for (int k = 0; k < 5 + 5 * layer; k++) {
#pragma unroll
                for (int i = 0; i < 8; i++) asm volatile("st.global.v4.u32 [%0], {%1,%1,%1,%1};" ::"l"(pre + 32 * i), "r"(~0u) : "memory");
                pre += k < 5 ? 256 : XCP / 8;
                if (k == 4) {
                    CSA(2);
                    asm volatile("fence.acq_rel.gpu;" ::: "memory");
                    asm volatile("fence.proxy.async.global;" ::: "memory");
                    __syncwarp();
                    if (tid == 288) mbar_arrive(bar_done);
                    CSA(3);
                    pre = reinterpret_cast<uint4*>(g_yT) + tile * (5 * XCP / 8) + (tid - 288);
                }
            }
            if (layer == 0) {
                asm volatile("griddepcontrol.launch_dependents;" ::: "memory");
                await_all(64, ld_epoch() * gridDim.x);
                CSA(5);
                float4 a[2] = {};
#pragma unroll
                for (int k = 0; k < 10; k++)
#pragma unroll
                    for (int h = 0; h < 2; h++) {
                        const int c4 = min(tid - 288 + 32 * h, 59);
                        const float4 v = __ldcg(reinterpret_cast<const float4*>(g_csp + (k / 5) * 9600 + (k % 5) * 640 + hg * 80) + c4 + (c4 / 20) * 780);
                        a[h].x += v.x; a[h].y += v.y; a[h].z += v.z; a[h].w += v.w;
                    }
#pragma unroll
                for (int h = 0; h < 2; h++)
#pragma unroll
                    for (int k = 0; k < 4; k++) {
                        const float c = 0.5f * (k == 0 ? a[h].x : k == 1 ? a[h].y : k == 2 ? a[h].z : a[h].w), c1 = c - rbf(c), c2 = c1 - rbf(c1);
                        *reinterpret_cast<uint4*>(stg + A1_SM_XB + (4 * min(tid - 288 + 32 * h, 59) + k) * 16) = make_uint4(pack2(c, c1), pack2(c2, 0.f), 0u, 0u);
                    }
                fence_async_smem();
                __syncwarp();
                if (one) {
                    bulk_store(g_xb + tile * 240, sbase + A1_SM_XB, 3840);
                    asm volatile("cp.async.bulk.commit_group;" ::: "memory");
                    asm volatile("cp.async.bulk.wait_group.read 0;" ::: "memory");
                    mbar_arrive(bar_stat);
                }
                __syncwarp();
                CSA(1);
            }
            TSTAMP1T(9, 288);
        } else {
            const int j = tid - 320;
            const uint32_t tag = ld_epoch();
            if (tid == 352) sm_started(layer);
            const int ch = j & 7, kg = (j >> 3) & 3;
            const unsigned char* src = stg + (layer ? (j >> 5) * 8192 + (hg & 3) * 2048 : A1_SM_W0 + (j >> 2) * 1280);
            const int of0 = layer ? kg * 128 + ((ch ^ kg) << 4) : (j & 7) << 4, ofx = layer ? 576 : 64, ofy = layer ? 1024 : 128;
            float s[8], q[8], p0[8];
#pragma unroll
            for (int i = 0; i < 8; i++) { s[i] = 0.f; q[i] = 0.f; }
#pragma unroll 1
            for (int it = 0; it < 5; it++) {
                uint4 v[4];
                mbar_wait(layer ? bars + 8 * (it % A1_NST) : bars + 240, layer * it / A1_NST);
#pragma unroll
                for (int k = 0; k < 4; k++) v[k] = *reinterpret_cast<const uint4*>(src + (layer ? (it % A1_NST) * A1_STAGE : it * 256) + (k & 1 ? of0 ^ ofx : of0) + (k >> 1) * ofy);
                if (it == 0) {
                    const uint4 pv = *reinterpret_cast<const uint4*>(src + (layer ? ch << 4 : 0));
                    const uint32_t w[4] = {pv.x, pv.y, pv.z, pv.w};
#pragma unroll
                    for (int i = 0; i < 4; i++) { p0[2 * i] = __uint_as_float((layer ? w[i] : w[0]) << 16); p0[2 * i + 1] = __uint_as_float(layer ? w[i] & 0xffff0000u : w[0] << 16); }
                }
                asm volatile("" :: "r"(v[0].x), "r"(v[1].x), "r"(v[2].x), "r"(v[3].x), "f"(p0[0]) : "memory");
                __syncwarp();
                if ((tid & 31) == 0) mbar_arrive(bar_rd + 8 * it);
#pragma unroll
                for (int k = 0; k < 4; k++) {
                    const uint32_t w[4] = {v[k].x, v[k].y, v[k].z, v[k].w};
#pragma unroll
                    for (int i = 0; i < 4; i++) {
                        const float a = __uint_as_float(w[i] << 16) - p0[2 * i], b = __uint_as_float(w[i] & 0xffff0000u) - p0[2 * i + 1];
                        s[2 * i] += a; s[2 * i + 1] += b; q[2 * i] = fmaf(a, a, q[2 * i]); q[2 * i + 1] = fmaf(b, b, q[2 * i + 1]);
                    }
                }
            }
            float o[4];
            int row;
            if (layer == 0) {
                float s0 = ((s[0] + s[1]) + (s[2] + s[3])) + ((s[4] + s[5]) + (s[6] + s[7])), q0 = ((q[0] + q[1]) + (q[2] + q[3])) + ((q[4] + q[5]) + (q[6] + q[7]));
#pragma unroll
                for (int o = 1; o <= 2; o <<= 1) { s0 += __shfl_xor_sync(~0u, s0, o); q0 += __shfl_xor_sync(~0u, q0, o); }
                if ((j & 3) == 0) {
                    const float d = s0 * (1.0f / DM);
                    const uint32_t ms = pack2(p0[0] + d, sqrt_apx(rbf(rbf(fmaxf(fmaf(-d, d, q0 * (1.0f / DM)), 0.f)) + 1e-5f)));
                    asm volatile("st.global.cg.u64 [%0], %1;" ::"l"(g_rstat + mb * 128 + (j & 4) * 16 + hg * 8 + (j >> 3)), "l"(tagw(ms, tag)) : "memory");
                    g_piv[mb * 128 + hg * 16 + ((j >> 2) & 8) + (j & 4) + ((j >> 3) & 3)] = __ushort_as_bfloat16((unsigned short)ms);
                }
                ulonglong2 v;
#pragma unroll 1
                for (int it = 0; it < SPIN_MAX; it++) {
                    v = ld_tag2(reinterpret_cast<const ulonglong2*>(g_rstat + mb * 128) + j);
                    if (__all_sync(~0u, tag_ok(v, tag))) break;
                    __nanosleep(100);
                }
                o[0] = __uint_as_float((uint32_t)v.x << 16); o[1] = rcp_apx(__uint_as_float((uint32_t)v.x & 0xffff0000u));
                o[2] = __uint_as_float((uint32_t)v.y << 16); o[3] = rcp_apx(__uint_as_float((uint32_t)v.y & 0xffff0000u));
                row = 2 * j;
            } else {
#pragma unroll
                for (int i = 0; i < 4; i++) {
                    const bool up = kg & 2;
                    const float ss = __shfl_xor_sync(~0u, up ? s[i] : s[i + 4], 16), qq = __shfl_xor_sync(~0u, up ? q[i] : q[i + 4], 16);
                    s[i] = (up ? s[i + 4] : s[i]) + ss; q[i] = (up ? q[i + 4] : q[i]) + qq; p0[i] = up ? p0[i + 4] : p0[i];
                }
#pragma unroll
                for (int i = 0; i < 2; i++) {
                    const bool up = kg & 1;
                    const float ss = __shfl_xor_sync(~0u, up ? s[i] : s[i + 2], 8), qq = __shfl_xor_sync(~0u, up ? q[i] : q[i + 2], 8);
                    s[i] = (up ? s[i + 2] : s[i]) + ss; q[i] = (up ? q[i + 2] : q[i]) + qq; p0[i] = up ? p0[i + 2] : p0[i];
                }
                uint4* gp = g_halo + 86016 + mb * 512 + j;
                const float d0 = s[0] * (1.0f / 80.0f), d1 = s[1] * (1.0f / 80.0f);
                asm volatile("st.relaxed.gpu.global.v4.f32 [%0], {%1,%2,%3,%4};" ::"l"(gp + hg * 64), "f"(p0[0] + d0), "f"(fmaxf(fmaf(-d0, s[0], q[0]), 0.f)), "f"(p0[1] + d1), "f"(fmaxf(fmaf(-d1, s[1], q[1]), 0.f)) : "memory");
                __nanosleep(ST_SLEEP0);
                uint32_t pw[8][4], todo = 0xff;
#pragma unroll 1
                for (int it = 0; it < SPIN_MAX; it++) {
#pragma unroll
                    for (int k = 0; k < 8; k++)
                        if (todo >> k & 1) asm volatile("ld.relaxed.gpu.global.v4.u32 {%0,%1,%2,%3}, [%4];" : "=r"(pw[k][0]), "=r"(pw[k][1]), "=r"(pw[k][2]), "=r"(pw[k][3]) : "l"(gp + k * 64) : "memory");
#pragma unroll
                    for (int k = 0; k < 8; k++)
                        if (__all_sync(~0u, pw[k][0] != ~0u && pw[k][1] != ~0u && pw[k][2] != ~0u && pw[k][3] != ~0u)) todo &= ~(1u << k);
                    if (!todo) break;
                    __nanosleep(ST_SLEEP);
                }
#pragma unroll
                for (int r = 0; r < 2; r++) {
                    float mean = 0.f, m2 = 0.f;
#pragma unroll
                    for (int k = 0; k < 8; k++) mean += __uint_as_float(pw[k][2 * r]);
                    mean *= 0.125f;
#pragma unroll
                    for (int k = 0; k < 8; k++) {
                        const float dm = __uint_as_float(pw[k][2 * r]) - mean;
                        m2 += fmaf(80.0f * dm, dm, __uint_as_float(pw[k][2 * r + 1]));
                    }
                    o[2 * r] = rbf(mean);
                    o[2 * r + 1] = rcp_apx(rbf(sqrt_apx(rbf(rbf(m2 * (1.0f / DM)) + 1e-5f))));
                }
                row = (j >> 5) * 64 + (j & 7) * 8 + ((j >> 3) & 3) * 2;
                if (hg == 0) *reinterpret_cast<uint32_t*>(g_piv + SEQ + mb * 128 + 2 * (row & 60) + 4 * (row >> 6) + (row & 3)) = __byte_perm(__float_as_uint(o[0]), __float_as_uint(o[2]), 0x7632);
            }
#pragma unroll
            for (int r = 0; r < 2; r++)
                *reinterpret_cast<uint4*>(stg + A1_SM_XA + (row + r) * 16) = make_uint4(__byte_perm(__float_as_uint(-o[2 * r]), 0, 0x3232), __float_as_uint(-o[2 * r]) >> 16, 0u, 0u);
            *reinterpret_cast<float4*>(rst + row + (row >> 6) * 8) = make_float4(o[0], o[1], o[2], o[3]);
            fence_async_smem();
            TSTAMP1T(7, 320); CSA(1);
            if (tid == 320) DBGC(44);
            __syncwarp();
            if ((tid & 31) == 0) mbar_arrive(bar_stat);
        }
        CSA(4); CSA_END;
        if (tid == 320) DBGCAL(0);
        if (tid == WOT) {
            mbar_wait(WO_LATE, 0);
            mbar_wait(bar_done, 0);
            bulk_load(sbase, wo + (hg * 8 + 6) * WOB, 2 * WOB, bar_wo);
            bulk_load(sbase + A1_SM_W0 + 2 * WOB, wo + (hg * 8 + 2) * WOB, WOB, bar_wo);
        }
        __syncwarp();
#define FWA 11
#define FWB 10
        if (w == FWA || w == FWB) {
            const int cw = w == FWB;
            const uint32_t* fl = reinterpret_cast<const uint32_t*>(rsum + 2 * SEQ) + (((layer * 16 + mb) * 2 + cw) * 8 + (tid & 7)) * FSTR;
            const unsigned char* src = reinterpret_cast<const unsigned char*>(of) + mb * 163840 + cw * 10240 + (tid & 7) * 20480;
            const uint32_t sl = sbase + (cw ? A1_SM_A1 : A1_SM_A0);
            mbar_wait(cw ? bar_done : bar_kvf, 0);
            if ((tid & 31) == 0) {
                mbar_expect_tx(bar_f2 + 64 * cw + 64, 10240);
                tma_load_3d(sl + 51200, &tmR, layer ? 0 : hg * 80, layer ? hg * 80 : mb * 64, layer ? mb * 2 + cw : cw, bar_f2 + 64 * cw + 64);
            }
            __syncwarp();
            uint32_t pend = 0xffu & ~(1u << hg), v = 0;
            const uint32_t bo = wo_off((tid & 7) + ((tid & 7) < hg)) >> 4, lt = (1u << (tid & 31)) - 1;
#pragma unroll 1
            for (int it = 0; pend && it < 2 * SPIN_MAX; it++) {
                if (v != 4 && (pend >> (tid & 31) & 1)) asm volatile(A1_FLD " %0, [%1];" : "=r"(v) : "l"(fl) : "memory");
                uint32_t fr;
                asm volatile("{\n.reg .pred p;\nmbarrier.test_wait.parity.shared::cta.b64 p, [%1], 0;\nselp.b32 %0, 1, 0, p;\n}" : "=r"(fr) : "r"(bar_e2 + 16 * cw + (tid & 1) * 8) : "memory");
                fr = __ballot_sync(~0u, fr);
                uint32_t m = __ballot_sync(~0u, v == 4 || it >= A1_FSPIN) & pend;
                const int q = 8 - __popc(pend) + __popc(m & lt);
                m &= __ballot_sync(~0u, q < ((fr & 2) ? 8 : (fr & 1) ? 7 : 5));
                pend ^= m;
                if (m >> (tid & 31) & 1) DBGC(12 + cw * 8 + (tid & 7));
                if (!m) __nanosleep(A1_FSLEEP);
                else asm volatile("fence.proxy.async.global;" ::: "memory");
                if (m >> (tid & 31) & 1) {
                    bulk_load(q == 7 && !cw ? sbase + A1_SM_W0 : sl + (q < 6 ? q : q - 6) * 10240, src, 10240, bar_f2 + 64 * cw + 8 * q);
                    asm volatile("st.shared.u32 [%0], %1;" ::"r"(que + 32 * cw + 4 * q), "r"(bo) : "memory");
                    mbar_expect_tx(bar_f2 + 64 * cw + 8 * q, 10240);
                    DBGC(44 + cw * 8 + q);
                }
                __syncwarp();
            }
        }
    } else if (tile < 128) {
        SPAN(1 + 4 * layer, 0);
        constexpr int on = 1;
        float acc[120];
        const int lane = tid & 31, warp = w & 7, g = lane >> 2, t = lane & 3;
        if (on) {
            SPAN(1 + 4 * layer, 1);
            TSTAMP1(0);
            if (threadIdx.x == 0) { GSTAMP(g_tim1, 15); }
            TSTAMP3(0);
            if (tid == 0) TSTAMP2(0);
            TSTAMP4(0);
            if (tid == 0) DBGC(60);
            if (layer == 0) a1_mainloop<0>(acc, sbase, bars, wg, tile); else a1_mainloop<1>(acc, sbase, bars, wg, tile);
            uint32_t ok;
            asm volatile("{\n.reg .pred p;\nmbarrier.test_wait.parity.shared::cta.b64 p, [%1], 0;\nselp.b32 %0, 1, 0, p;\n}" : "=r"(ok) : "r"(bar_stat) : "memory");
            if (tid == 128 && !ok) mbar_arrive(bars + 160);
            __syncwarp();
            mbar_wait(bar_stat, 0);
            wgmma_fence();
            wgmma_n240<0, 0>(acc, make_desc(sbase + A1_SM_XA + wg * 1024, 0, 128, 0), make_desc(sbase + A1_SM_XB, 0, 128, 0), 1);
            wgmma_commit();
            if (tid == 128 && ok) mbar_arrive(bars + 160);
            mbar_wait(bars + 8 * (A1_NST + 3), 1);
        }
        const float2* rw = rst + 16 * warp + 8 * wg;
        const float rb0 = rw[g + 8].y, ra = rw[g].y * 0.22360679774997896f, rb = rb0 * 0.22360679774997896f;
        wgmma_wait<0>();
        if ((tid & 127) == 0) mbar_arrive(bar_done);
        TSTAMP1(2); CSA(1);
        TSTAMP1T(13, 224);
        if ((tid & 127) == 0) DBGC(62 - wg);
        uint32_t f[2][30];
#pragma unroll
        for (int j = 10; j < 30; j++) f[1][j] = pack2(acc[4 * j + 2], acc[4 * j + 3]);
        if ((warp & 3) == 3) {
            uint4* hout = g_halo + (((layer * 16 + mb) * 8 + hg) * 2 + wg) * 168;
#pragma unroll
            for (int j = 0; j < 20; j += 4)
                asm volatile("st.relaxed.gpu.global.v4.u32 [%0], {%1,%2,%3,%4};" ::"l"(hout + 8 * j + lane), "r"(f[1][10 + j]), "r"(f[1][11 + j]), "r"(f[1][12 + j]), "r"(f[1][13 + j]) : "memory");
            if (t == 0) asm volatile("st.relaxed.gpu.global.f32 [%0], %1;" ::"l"(reinterpret_cast<float*>(hout + 160) + g), "f"(rb0) : "memory");
        }
        TSTAMP1T(12, 224);
        const uint32_t kvw = sbase + A1_SM_KV + (16 * warp + 8 * wg) * A1_KVP;
        const uint32_t mrow = kvw + (lane & 7) * A1_KVP + (lane >> 3) * 16;
#pragma unroll
        for (int j = 0; j < 20; j += 4) stsm_x4(mrow + 16 * A1_KVP + 16 * j, f[1][10 + j], f[1][11 + j], f[1][12 + j], f[1][13 + j]);
        __syncwarp();
        if (lane == 0 && (warp & 3) != 3) mbar_arrive(bar_kv + 8 * (warp + 1));
#pragma unroll
        for (int j = 0; j < 30; j++) f[0][j] = pack2(acc[4 * j], acc[4 * j + 1]);
        stsm_x4(mrow + 8 * A1_KVP + 160, f[0][20], f[0][21], f[0][22], f[0][23]);
        stsm_x4(mrow + 8 * A1_KVP + 224, f[0][24], f[0][25], f[0][26], f[0][27]);
        asm volatile("stmatrix.sync.aligned.m8n8.x2.shared.b16 [%0], {%1,%2};" ::"r"(mrow + 8 * A1_KVP + 288), "r"(f[0][28]), "r"(f[0][29]) : "memory");
#pragma unroll
        for (int j = 0; j < 10; j++) f[1][j] = pack2(acc[4 * j + 2], acc[4 * j + 3]);
        __syncwarp();
        uint32_t vb[10][2], vp[12], kp[12];
#pragma unroll
        for (int j = 0; j < 10; j += 2) ldsm_x4_t(&vb[j][0], kvw + (8 + (lane & 15)) * A1_KVP + 160 + (lane >> 4) * 16 + 16 * j);
        const bool up0 = 2 * t > g, up1 = 2 * t + 1 > g, edge = (mb | (warp & 3)) == 0;
        float rk[4];
        auto above = [&]() {
            mbar_wait(bar_kv + 8 * warp, 0);
#pragma unroll
            for (int j = 0; j < 12; j += 4) ldsm_x4(&kp[j], mrow + 16 * j);
            rk[0] = rw[2 * t - (up0 ? 8 : 0)].y; rk[1] = rw[2 * t + 1 - (up1 ? 8 : 0)].y;
#pragma unroll
            for (int j = 0; j < 12; j += 4) ldsm_x4_t(&vp[j], mrow + 160 + 16 * j - (j == 8 ? (lane & 16) * 2 : 0));
            __syncwarp();
            if (lane == 0) mbar_arrive(bar_kvf);
        };
        auto halo = [&]() {
            if (lane == 0) mbar_arrive(bar_kvf);
            const uint4* hin = g_halo + (((layer * 16 + mb - 1) * 8 + hg) * 2 + wg) * 168;
            uint32_t hv[22] = {};
            rk[0] = rw[2 * t].y; rk[1] = rw[2 * t + 1].y;
            if (mb > 0) {
#pragma unroll 1
                for (int it = 0; it < SPIN_MAX; it++) {
#pragma unroll
                    for (int k = 0; k < 20; k += 4)
                        asm volatile("ld.relaxed.gpu.global.v4.u32 {%0,%1,%2,%3}, [%4];" : "=r"(hv[k]), "=r"(hv[k + 1]), "=r"(hv[k + 2]), "=r"(hv[k + 3]) : "l"(hin + 8 * k + lane) : "memory");
                    asm volatile("ld.relaxed.gpu.global.v2.u32 {%0,%1}, [%2];" : "=r"(hv[20]), "=r"(hv[21]) : "l"(reinterpret_cast<const uint2*>(hin + 160) + t) : "memory");
                    uint32_t m = max(hv[20], hv[21]);
#pragma unroll
                    for (int k = 0; k < 20; k += 2) m = __vimax3_u32(m, hv[k], hv[k + 1]);
                    if (!__any_sync(~0u, m == ~0u)) break;
                }
            }
            if (lane == 0) DBGC(52 - 16 * wg);
#pragma unroll
            for (int j = 0; j < 10; j++) {
                kp[j] = hv[j];
                asm volatile("movmatrix.sync.aligned.m8n8.trans.b16 %0, %1;" : "=r"(vp[j]) : "r"(hv[10 + j]));
            }
            if (up0) rk[0] = __uint_as_float(hv[20]);
            if (up1) rk[1] = __uint_as_float(hv[21]);
        };
        rk[2] = rw[2 * t + (up0 ? 0 : 8)].y; rk[3] = rw[2 * t + 1 + (up1 ? 0 : 8)].y;
        uint32_t qs[4][2];
#pragma unroll
        for (int h = 0; h < 4; h++) {
            qs[h][0] = (t >> 1) == (h & 1) ? f[0][5 * (h >> 1) + 2] : 0u; qs[h][1] = (t >> 1) == (h & 1) ? f[1][5 * (h >> 1) + 2] : 0u;
            asm volatile("" : "+r"(qs[h][0]), "+r"(qs[h][1]));
        }
#pragma unroll
        for (int j = 0; j < 10; j++) asm volatile("" : "+r"(f[0][j]), "+r"(f[1][j]), "+r"(f[0][10 + j]));
        if (warp & 3) above(); else if (wg) halo();
        TSTAMP1T(10, 64); CSA(2);
        if (warp && !wg) mbar_wait(bars + 416 + 8 * warp, 0);
        CSA(3);
        float sc[4][3][4];
#pragma unroll
        for (int h = 0; h < 4; h++) {
            const int jb = 5 * (h >> 1) + 3 * (h & 1), js = 5 * (h >> 1) + 2;
#pragma unroll
            for (int nt = 1; nt < 3; nt++) {
#pragma unroll
                for (int e = 0; e < 4; e++) sc[h][nt][e] = 0.f;
                mma_bf16(sc[h][nt], f[0][jb], f[1][jb], f[0][jb + 1], f[1][jb + 1], f[nt - 1][10 + jb], f[nt - 1][11 + jb]);
                mma_bf16_k8(sc[h][nt], qs[h][0], qs[h][1], f[nt - 1][10 + js]);
            }
        }
        if (warp == 0) halo();
        TSTAMP1(8); CSA(4);
#pragma unroll
        for (int h = 0; h < 4; h++) {
            const int jb = 5 * (h >> 1) + 3 * (h & 1), js = 5 * (h >> 1) + 2;
#pragma unroll
            for (int e = 0; e < 4; e++) sc[h][0][e] = 0.f;
            mma_bf16(sc[h][0], f[0][jb], f[1][jb], f[0][jb + 1], f[1][jb + 1], kp[jb], kp[jb + 1]);
            mma_bf16_k8(sc[h][0], qs[h][0], qs[h][1], kp[js]);
        }
        TSTAMP1T(3, 64);
        float p[4][4], sum[4][2];
        uint32_t lg[4][2], mx[4];
        const float rl[4] = {rk[0] * ra, rk[1] * ra, rk[2] * rb, rk[3] * rb};
        auto max2 = [](uint32_t a, uint32_t b) { uint32_t r; asm("max.bf16x2 %0, %1, %2;" : "=r"(r) : "r"(a), "r"(b)); return r; };
#pragma unroll
        for (int h = 0; h < 4; h++) {
            lg[h][0] = pack2((up0 ? sc[h][0][0] : sc[h][1][0]) * rl[0], (up0 ? sc[h][1][2] : sc[h][2][2]) * rl[2]);
            lg[h][1] = pack2((up1 ? sc[h][0][1] : sc[h][1][1]) * rl[1], (up1 ? sc[h][1][3] : sc[h][2][3]) * rl[3]);
            if (edge) {
                if (up0) lg[h][0] = __byte_perm(lg[h][0], 0xce6eu, 0x3254);
                if (up1) lg[h][1] = __byte_perm(lg[h][1], 0xce6eu, 0x3254);
            }
            mx[h] = max2(lg[h][0], lg[h][1]);
        }
#pragma unroll
        for (int o = 1; o <= 2; o <<= 1)
#pragma unroll
            for (int h = 0; h < 4; h++) mx[h] = max2(mx[h], __shfl_xor_sync(~0u, mx[h], o));
#pragma unroll
        for (int h = 0; h < 4; h++)
#pragma unroll
            for (int r = 0; r < 2; r++) {
                const float m = __uint_as_float(r ? mx[h] & 0xffff0000u : mx[h] << 16);
#pragma unroll
                for (int e = 0; e < 2; e++)
                    asm("ex2.approx.ftz.f32 %0, %1;" : "=f"(p[h][2 * r + e]) : "f"((__uint_as_float(r ? lg[h][e] & 0xffff0000u : lg[h][e] << 16) - m) * 1.4426950408889634f));
                sum[h][r] = p[h][2 * r] + p[h][2 * r + 1];
            }
#pragma unroll
        for (int o = 1; o <= 2; o <<= 1)
#pragma unroll
            for (int h = 0; h < 4; h++)
#pragma unroll
                for (int r = 0; r < 2; r++) sum[h][r] += __shfl_xor_sync(~0u, sum[h][r], o);
        TSTAMP1T(5, 64); CSA(5);
        const uint32_t mu = (up0 ? 0xffffu : 0u) | (up1 ? 0xffff0000u : 0u);
        uint32_t ob[10][2];
#pragma unroll
        for (int P = 0; P < 2; P++) {
            float os[2][4];
#pragma unroll
            for (int e = 0; e < 2; e++) {
                const int h = 2 * P + e;
                const float i0 = rcp_apx(sum[h][0]), i1 = rcp_apx(sum[h][1]);
                const uint32_t w0 = pack2(p[h][0] * rk[0] * i0, p[h][1] * rk[1] * i0), w1 = pack2(p[h][2] * rk[2] * i1, p[h][3] * rk[3] * i1);
#pragma unroll
                for (int dt = 0; dt < 3; dt++) {
                    const int j = 5 * P + (dt < 2 ? 3 * e + dt : 2);
                    float o[4] = {0.f, 0.f, 0.f, 0.f};
                    mma_bf16(o, w0 & ~mu, w1 & mu, 0u, w1 & ~mu, vb[j][0], vb[j][1]);
                    mma_bf16_k8(o, w0 & mu, 0u, vp[j]);
                    if (dt < 2) { ob[j][0] = pack2(o[0], o[1]); ob[j][1] = pack2(o[2], o[3]); }
                    else { os[e][0] = o[0]; os[e][1] = o[1]; os[e][2] = o[2]; os[e][3] = o[3]; }
                }
            }
#pragma unroll
            for (int k = 0; k < 4; k++) os[0][k] = t < 2 ? os[0][k] : os[1][k];
            ob[5 * P + 2][0] = pack2(os[0][0], os[0][1]); ob[5 * P + 2][1] = pack2(os[0][2], os[0][3]);
        }
        const uint32_t sl = sbase + (wg ? A1_SM_A1 : A1_SM_A0);
        const uint32_t o0 = (warp & 3) * 2048 + g * 64 + ((t ^ (g >> 1)) << 4), o1 = 8192 + (warp & 3) * 512 + g * 32 + ((t ^ ((g >> 2) << 1)) << 3);
        CSA(15);
        mbar_wait(bar_done, 0);
        if (wg == 0) mbar_wait(bar_kvf, 0);
#pragma unroll
        for (int h = 0; h < 2; h++) {
            asm volatile("st.shared.v4.u32 [%0], {%1,%2,%3,%4};" ::"r"(sl + o0 + h * 1024), "r"(ob[0][h]), "r"(ob[1][h]), "r"(ob[2][h]), "r"(ob[3][h]) : "memory");
            asm volatile("st.shared.v4.u32 [%0], {%1,%2,%3,%4};" ::"r"(sl + o0 + h * 1024 + 512), "r"(ob[4][h]), "r"(ob[5][h]), "r"(ob[6][h]), "r"(ob[7][h]) : "memory");
            asm volatile("st.shared.v2.u32 [%0], {%1,%2};" ::"r"(sl + o1 + h * 256), "r"(ob[8][h]), "r"(ob[9][h]) : "memory");
        }
        if (wg && lane == 0) mbar_arrive(bars + 384 + 8 * warp);
        fence_async_smem();
        __syncwarp();
        TSTAMP1T(4, 64); CSA(6);
        TSTAMP1(1);
        TSTAMP2(1);
        const unsigned char* ot = reinterpret_cast<const unsigned char*>(of) + mb * 163840 + wg * 10240;
        if (lane == 0) {
            asm volatile("cp.async.bulk.global.shared::cta.bulk_group [%0], [%1], 2048;" ::"l"(ot + hg * 20480 + (warp & 3) * 2048), "r"(sl + (warp & 3) * 2048) : "memory");
            asm volatile("cp.async.bulk.global.shared::cta.bulk_group [%0], [%1], 512;" ::"l"(ot + hg * 20480 + 8192 + (warp & 3) * 512), "r"(sl + 8192 + (warp & 3) * 512) : "memory");
            asm volatile("cp.async.bulk.commit_group;" ::: "memory");
            if (wg == 0) mbar_arrive(bar_pv);
            asm volatile("cp.async.bulk.wait_group 0;" ::: "memory");
            asm volatile(A1_FRED " [%0], 1;" ::"l"(reinterpret_cast<uint32_t*>(rsum + 2 * SEQ) + (((layer * 16 + mb) * 2 + wg) * 8 + hg) * FSTR) : "memory");
            DBGC(4 + warp);
        }
        TSTAMP4(11); CSA(7);
        float ac2[40];
        const uint64_t db0 = make_desc(sbase, 1024, 256, 3), db1 = make_desc(sbase + 10240, 512, 256, 3), da0 = make_desc(sl, 16, 1024, 2), da1 = make_desc(sl + 8192, 16, 256, 3);
        const uint32_t o7 = wg ? 640 : (A1_SM_W0 - A1_SM_A0) >> 4;
        const uint32_t trow = ((lane & 7) + 8 * (lane >> 4)) * 128 + (((2 * (warp & 3) + ((lane >> 3) & 1)) ^ (lane & 7)) << 4);
        uint32_t xr[10][2];
        mbar_wait(bar_f2 + 64 * wg + 64, 0);
        if (layer == 0) {
#pragma unroll
            for (int j = 0; j < 10; j += 2) ldsm_x4(&xr[j][0], sl + 51200 + (16 * (warp & 3) + (lane & 15)) * 160 + (lane >> 4) * 16 + 16 * j);
        } else {
#pragma unroll
            for (int j = 0; j < 10; j += 2) ldsm_x4_t(&xr[j][0], sl + 51200 + trow + 1024 * j);
        }
        const uint32_t ri = __shfl_sync(~0u, layer * SEQ + (wg * 2 + ((g >> 1) & 1)) * 512 + (mb * 16 + 4 * (warp & 3) + (g >> 2)) * 2 + (g & 1), lane);
        mbar_wait(bar_wo, 0);
        if (wg) mbar_wait(bar_pv, 0);
        if (wg) asm volatile("bar.sync 2, 128;" ::: "memory"); else asm volatile("bar.sync 1, 128;" ::: "memory");
        TSTAMP2(2); CSA(8);
#pragma unroll
        for (int q = 0; q < 8; q++) {
            uint32_t bo = wo_off(0) >> 4;
            if (q) {
                mbar_wait(bar_f2 + 64 * wg + 8 * q, 0);
                asm volatile("ld.shared.u32 %0, [%1];" : "=r"(bo) : "r"(que + 32 * wg + 4 * q) : "memory");
                bo = __shfl_sync(~0u, bo, 0);
                TSTAMP4(q);
                if (q % 3 == 1) CSA(9 + q / 3);
                if (q == 1 && (tid & 127) == 0) DBGC(29 + 8 * wg);
            }
            wgmma_fence();
#pragma unroll
            for (int j = 0; j < 5; j++) wgmma_n80(ac2, (j < 4 ? da0 : da1) + (q == 7 ? o7 : 0u) + (uint64_t)((q < 6 ? q * 640 : 0) + (j & 2) * 16 + (j & 1) * 2), (j < 4 ? db0 : db1) + bo + (uint64_t)((j & 2) * 160 + (j & 1) * 32), j || q);
            wgmma_commit();
            if (q == 0) {
                wgmma_wait<0>();
                if ((tid & 127) == 0) { mbar_arrive(bar_e2 + 16 * wg); mbar_arrive(bar_e2 + 8); }
            }
            if (q == 2 && wg) {
                wgmma_wait<1>();
                if (tid == 128) mbar_arrive(bar_e2 + 24);
            }
        }
        if ((tid & 127) == 0) DBGC(28 + wg * 8 + 7);
        TSTAMP2(3);
        wgmma_wait<0>();
        TSTAMP2(4); CSA(12);
        if (__any_sync(~0u, ac2[0] != ac2[0] || ac2[2] != ac2[2])) {
#pragma unroll
            for (int i = 0; i < 40; i++) ac2[i] = 0.f;
            uint32_t a[20], an[20];
            auto lda = [&](uint32_t (&r)[20], int h) {
#pragma unroll
                for (int u = 0; u < 4; u++)
                    asm volatile("ld.relaxed.gpu.global.v4.u32 {%0,%1,%2,%3}, [%4];" : "=r"(r[4 * u]), "=r"(r[4 * u + 1]), "=r"(r[4 * u + 2]), "=r"(r[4 * u + 3]) : "l"(ot + h * 20480 + o0 + u * 512) : "memory");
#pragma unroll
                for (int u = 0; u < 2; u++)
                    asm volatile("ld.relaxed.gpu.global.v2.u32 {%0,%1}, [%2];" : "=r"(r[16 + 2 * u]), "=r"(r[17 + 2 * u]) : "l"(ot + h * 20480 + o1 + u * 256) : "memory");
            };
            lda(an, 0);
#pragma unroll 5
            for (int k = lane; k < WOB / 16; k += 32)
                reinterpret_cast<uint4*>(stg + (sl - sbase))[k] = __ldcg(reinterpret_cast<const uint4*>(wo + hg * 8 * WOB) + k);
            __syncwarp();
#pragma unroll 1
            for (int h = 0; h < 8; h++) {
#pragma unroll 1
                for (int it = 0; it < SPIN_MAX; it++) {
                    uint32_t m = 0;
#pragma unroll
                    for (int k = 0; k < 20; k += 2) m = __vimax3_u32(m, an[k], an[k + 1]);
                    if (!__any_sync(~0u, m == ~0u)) break;
                    lda(an, h);
                }
#pragma unroll
                for (int k = 0; k < 20; k++) a[k] = an[k];
                lda(an, min(h + 1, 7));
                const uint32_t bp = h == hg ? sl : sbase + wo_off(h + (h < hg));
                const int r0 = 8 * ((lane & 7) >> 1) + 2 * (lane >> 3) + (lane & 1), r2 = 4 * ((lane & 7) >> 1) + 2 * ((lane >> 3) & 1) + (lane & 1);
#pragma unroll
                for (int n = 0; n < 10; n++) {
                    uint32_t b[12];
                    ldsm_x4_t(b, bp + (n >> 1) * 1024 + r0 * 32 + (((n ^ (r0 >> 2)) & 1) << 4));
                    ldsm_x4_t(b + 4, bp + 5120 + (n >> 1) * 1024 + r0 * 32 + (((n ^ (r0 >> 2)) & 1) << 4));
                    ldsm_x4_t(b + 8, bp + 10240 + (n >> 1) * 512 + r2 * 32 + (((n ^ (r2 >> 2)) & 1) << 4));
                    mma_bf16(ac2 + 4 * n, a[0], a[8], a[1], a[9], b[0], b[1]); mma_bf16(ac2 + 4 * n, a[2], a[10], a[3], a[11], b[2], b[3]);
                    mma_bf16(ac2 + 4 * n, a[4], a[12], a[5], a[13], b[4], b[5]); mma_bf16(ac2 + 4 * n, a[6], a[14], a[7], a[15], b[6], b[7]);
                    mma_bf16(ac2 + 4 * n, a[16], a[18], a[17], a[19], b[8], b[9]);
                }
            }
        }
#pragma unroll
        for (int j = 0; j < 10; j++)
#pragma unroll
            for (int hh = 0; hh < 2; hh++) {
                const uint32_t a = pack2(ac2[4 * j + 2 * hh], ac2[4 * j + 2 * hh + 1]);
                const __nv_bfloat162 r = __hadd2_rn(*reinterpret_cast<const __nv_bfloat162*>(&xr[j][hh]), *reinterpret_cast<const __nv_bfloat162*>(&a));
                xr[j][hh] = *reinterpret_cast<const uint32_t*>(&r);
            }
        const uint32_t so = sl + 30720;
#pragma unroll
        for (int j = 0; j < 10; j += 2) stsm_x4_t(so + trow + 1024 * j, xr[j][0], xr[j][1], xr[j + 1][0], xr[j + 1][1]);
        if (wg) asm volatile("bar.sync 2, 128;" ::: "memory"); else asm volatile("bar.sync 1, 128;" ::: "memory");
        TSTAMP2(5); CSA(13);
        if ((tid & 127) == 0) {
            fence_async_smem();
            asm volatile("cp.async.bulk.tensor.2d.global.shared::cta.bulk_group [%0, {%1, %2}], [%3];" ::"l"(&tmX1), "r"(mb * 128 + 64 * wg), "r"(hg * 80), "r"(so) : "memory");
            asm volatile("cp.async.bulk.commit_group;" ::: "memory");
        }
        __syncwarp();
        const float p0 = *(volatile const float*)&rw[g].x, p1 = *(volatile const float*)&rw[g + 8].x;
        float s[3][4] = {};
        const uint32_t pp[2] = {__byte_perm(__float_as_uint(p0), 0, 0x3232), __byte_perm(__float_as_uint(p1), 0, 0x3232)};
#pragma unroll
        for (int j = 0; j < 10; j += 2) {
            const uint32_t d0 = sub2(xr[j][0], pp[0]), d1 = sub2(xr[j][1], pp[1]), d2 = sub2(xr[j + 1][0], pp[0]), d3 = sub2(xr[j + 1][1], pp[1]);
            mma_bf16(s[0], xr[j][0], xr[j][1], xr[j + 1][0], xr[j + 1][1], 0x3f803f80u, 0x3f803f80u);
            mma_bf16(s[1], d0, d1, d2, d3, d0, d2);
            mma_bf16(s[2], d0, d1, d2, d3, d1, d3);
        }
        if (t == (g >> 1)) {
            float2* rp = rsum + ri;
            asm volatile("red.relaxed.gpu.global.add.v2.f32 [%0], {%1, %2};" ::"l"(rp), "f"(fmaf(-80.f, p0, s[0][0])), "f"((g & 1) ? s[1][1] : s[1][0]) : "memory");
            asm volatile("red.relaxed.gpu.global.add.v2.f32 [%0], {%1, %2};" ::"l"(rp + 4), "f"(fmaf(-80.f, p1, s[0][2])), "f"((g & 1) ? s[2][3] : s[2][2]) : "memory");
        }
        asm volatile("cp.async.bulk.wait_group.read 0;" ::: "memory");
        TSTAMP2(6); CSA(14); CSA_END;
        if (tid == 0) DBGC(63);
        if (tid == 128) DBGC(28);
        if (tid == 0) DBGCAL(2);
        GSTAMP(g_tim1, 14);
        SPAN(1 + 4 * layer, 3);
    }
#undef layer
}

static int h_nsm;
static void* h_sym[11];
static TileTab h_tab[2];
static CUtensorMap h_tmX0, h_tmX1, h_tmR0, h_tmR1, h_tmX1st, h_tmOut;
static KgMaps h_tmW;
typedef CUresult (*PFN_encodeTiled)(CUtensorMap*, CUtensorMapDataType, cuuint32_t, void*, const cuuint64_t*, const cuuint64_t*,
                                    const cuuint32_t*, const cuuint32_t*, CUtensorMapInterleave, CUtensorMapSwizzle,
                                    CUtensorMapL2promotion, CUtensorMapFloatOOBfill);
static void make_tmap(CUtensorMap* tm, const void* ptr, uint64_t cols, uint64_t rows, uint32_t bc, uint32_t br, CUtensorMapSwizzle sw, uint64_t pitch = 0, uint64_t hi = 0, uint32_t bh = 2) {
    static PFN_encodeTiled fn = nullptr;
    if (!fn) {
        void* p = nullptr; cudaDriverEntryPointQueryResult qr;
        cudaGetDriverEntryPoint("cuTensorMapEncodeTiled", &p, cudaEnableDefault, &qr);
        fn = (PFN_encodeTiled)p;
    }
    if (br == 0) {
        cuuint64_t dims[5] = {16, 2, rows / 8, 4, cols / 16}; cuuint64_t strides[4] = {cols * 2, cols * 16, cols * 4, 32};
        cuuint32_t box[5] = {16, 2, bc, 4, 5}; cuuint32_t es[5] = {1, 1, 1, 1, 1};
        fn(tm, CU_TENSOR_MAP_DATA_TYPE_BFLOAT16, 5, const_cast<void*>(ptr), dims, strides, box, es, CU_TENSOR_MAP_INTERLEAVE_NONE, sw,
           CU_TENSOR_MAP_L2_PROMOTION_L2_128B, CU_TENSOR_MAP_FLOAT_OOB_FILL_NONE);
        return;
    }
    if (hi == 16) {
        cuuint64_t dims[4] = {16, 32, 120, 20}; cuuint64_t strides[3] = {3840, 32, 32 * 3840};
        cuuint32_t box[4] = {16, 32, 5, 2}; cuuint32_t es[4] = {1, 1, 1, 1};
        fn(tm, CU_TENSOR_MAP_DATA_TYPE_BFLOAT16, 4, const_cast<void*>(ptr), dims, strides, box, es, CU_TENSOR_MAP_INTERLEAVE_NONE, sw,
           CU_TENSOR_MAP_L2_PROMOTION_L2_128B, CU_TENSOR_MAP_FLOAT_OOB_FILL_NONE);
        return;
    }
    if (bh == 0) {
        cuuint64_t dims[5] = {64, 64, 2, 16, 10}; cuuint64_t strides[4] = {pitch * 2, hi * 2, cols * 2, rows * 2};
        cuuint32_t box[5] = {64, 64, 2, 1, 1}; cuuint32_t es[5] = {1, 1, 1, 1, 1};
        fn(tm, CU_TENSOR_MAP_DATA_TYPE_BFLOAT16, 5, const_cast<void*>(ptr), dims, strides, box, es, CU_TENSOR_MAP_INTERLEAVE_NONE, sw,
           CU_TENSOR_MAP_L2_PROMOTION_L2_128B, CU_TENSOR_MAP_FLOAT_OOB_FILL_NONE);
        return;
    }
    if (hi) {
        cuuint64_t dims[3] = {cols, rows, hi == 64 ? 32u : 2u}; cuuint64_t strides[2] = {pitch * 2, hi * 2};
        cuuint32_t box[3] = {bc, br, bh}; cuuint32_t es[3] = {1, 1, 1};
        fn(tm, CU_TENSOR_MAP_DATA_TYPE_BFLOAT16, 3, const_cast<void*>(ptr), dims, strides, box, es, CU_TENSOR_MAP_INTERLEAVE_NONE, sw,
           CU_TENSOR_MAP_L2_PROMOTION_L2_128B, CU_TENSOR_MAP_FLOAT_OOB_FILL_NONE);
        return;
    }
    cuuint64_t dims[2] = {cols, rows}; cuuint64_t strides[1] = {(pitch ? pitch : cols) * 2};
    cuuint32_t box[2] = {bc, br}; cuuint32_t es[2] = {1, 1};
    fn(tm, CU_TENSOR_MAP_DATA_TYPE_BFLOAT16, 2, const_cast<void*>(ptr), dims, strides, box, es, CU_TENSOR_MAP_INTERLEAVE_NONE, sw,
       CU_TENSOR_MAP_L2_PROMOTION_L2_128B, CU_TENSOR_MAP_FLOAT_OOB_FILL_NONE);
}
template <typename... Args>
static void launch_pdl(void (*kern)(Args...), int grid, int block, int smem, Args... args) {
    cudaLaunchConfig_t cfg = {};
    cfg.gridDim = dim3(grid); cfg.blockDim = dim3(block); cfg.dynamicSmemBytes = smem; cfg.stream = cudaStreamPerThread;
    cudaLaunchAttribute at[1];
    at[0].id = cudaLaunchAttributeProgrammaticStreamSerialization; at[0].val.programmaticStreamSerializationAllowed = 1;
    cfg.attrs = at; cfg.numAttrs = 1;
    cudaLaunchKernelEx(&cfg, kern, args...);
}
static void launch_stage(int k, void* const* d_in, void* d_out) {
    const Par par = {k > 1 ? nullptr : (const bf16*)d_in[4], (const bf16*)d_in[5], (const bf16*)d_in[6], (const bf16*)d_in[7], (const bf16*)d_in[8], (const bf16*)d_in[9], k > 1, 0, (const bf16*)d_in[0],
                     (uint4*)h_sym[4], (uint4*)h_sym[2], (uint4*)h_sym[6], (uint4*)h_sym[3], (uint4*)h_sym[0], (float*)h_sym[5], (uint4*)h_sym[1], (const bf16*)d_in[1], (const bf16*)d_in[2]};
    auto a1 = h_nsm == 132 ? a1_kernel<true> : a1_kernel<false>;
    switch (k) {
        case 1: a1<<<h_nsm, A1_THREADS, A1_SMEM, cudaStreamPerThread>>>(par, h_tmX0, h_tmR0, h_tmX1st, h_tmW, h_tab[0]); break;
        case 3: launch_pdl(conv_kernel, DM / CV_CPB, CV_THREADS, CV_SMEM, 0, (const uint4*)h_sym[7], (const float4*)h_sym[4], (const bf16*)h_sym[8], (bf16*)h_sym[9], (const uint4*)h_sym[0], h_tmOut); break;
        case 5: launch_pdl(a1, h_nsm, A1_THREADS, A1_SMEM, par, h_tmX1, h_tmR1, h_tmX1st, h_tmW, h_tab[1]); break;
        case 7: launch_pdl(conv_kernel, DM / CV_CPB, CV_THREADS, CV_SMEM, 1, (const uint4*)h_sym[7] + SEQ / 8, (const float4*)h_sym[4] + SEQ / 2, (const bf16*)h_sym[8], (bf16*)h_sym[10], (const uint4*)h_sym[0], h_tmOut); break;
        default: break;
    }
}
static int n_stage_kernels() { return 9; }
static const char* stage_name(int k) { const char* n[] = {"kgen", "a1", "a2", "conv", "tr", "a1", "a2", "conv", "tr"}; return n[k]; }

extern "C" void kernel_launch(void* const* d_in, const int* in_sizes, int n_in, void* d_out, int out_size) {
    (void)in_sizes; (void)n_in; (void)out_size;
    static const void *p_in = nullptr, *p_w1 = nullptr, *p_w2 = nullptr, *p_out = nullptr;
    if (p_in != d_in[0] || p_w1 != d_in[1] || p_w2 != d_in[2] || p_out != d_out) {
        cudaFuncSetAttribute(conv_kernel, cudaFuncAttributeMaxDynamicSharedMemorySize, CV_SMEM);
        cudaFuncSetAttribute(a1_kernel<true>, cudaFuncAttributeMaxDynamicSharedMemorySize, A1_SMEM);
        cudaFuncSetAttribute(a1_kernel<false>, cudaFuncAttributeMaxDynamicSharedMemorySize, A1_SMEM);
        int dev; cudaGetDevice(&dev); cudaDeviceGetAttribute(&h_nsm, cudaDevAttrMultiProcessorCount, dev);
        if (h_nsm != 132) h_nsm = 128;
        cudaGetSymbolAddress(&h_sym[0], g_tap); cudaGetSymbolAddress(&h_sym[1], g_wq); cudaGetSymbolAddress(&h_sym[2], g_wo);
        cudaGetSymbolAddress(&h_sym[3], g_halo); cudaGetSymbolAddress(&h_sym[4], g_sum); cudaGetSymbolAddress(&h_sym[5], g_csp); cudaGetSymbolAddress(&h_sym[6], g_of);
        cudaGetSymbolAddress(&h_sym[7], g_piv); cudaGetSymbolAddress(&h_sym[8], g_x1T); cudaGetSymbolAddress(&h_sym[9], g_xcT); cudaGetSymbolAddress(&h_sym[10], g_yT);
        for (int i = 0; i < 264; i++) {
            const int s = i % 132, h = (s - 64) >> 1;
            const int t = h_nsm != 132 ? s : s < 64 ? ((s >> 1) & 7) * 16 + (s >> 4) * 2 + (s & 1) : s < 120 ? (1 + h % 7) * 16 + 8 + (h / 7) * 2 + (s & 1) : s < 124 ? 128 : s - 116;
            const int hg = (4 * (t >> 6) + (t & 3)) & 7;
            const uint64_t wp = (uint64_t)h_sym[1] + hg * 10 * WQ_STAGE;
            h_tab[i / 132].e[s] = make_uint4((uint32_t)wp, (uint32_t)(wp >> 32), ((t >> 2) & 15) | (i / 132) << 4 | hg << 8 | 5 * (hg >> 2) << 16 | (uint32_t)t << 24, 0);
        }
        void *px1, *px2;
        cudaGetSymbolAddress(&px1, g_x1T); cudaGetSymbolAddress(&px2, g_xcT);
        make_tmap(&h_tmX0, d_in[0], 128 * 640, 64, 64, 64, CU_TENSOR_MAP_SWIZZLE_128B, 1280, 640, 0);
        make_tmap(&h_tmX1, px2, 128, 64 * XCP, 64, 64, CU_TENSOR_MAP_SWIZZLE_128B, XCP, 64, 0);
        make_tmap(&h_tmR0, d_in[0], 640, 1024, 80, 64, CU_TENSOR_MAP_SWIZZLE_NONE, 1280, 640, 1);
        make_tmap(&h_tmR1, px2, 64, 640, 64, 80, CU_TENSOR_MAP_SWIZZLE_128B, XCP, 64, 1);
        make_tmap(&h_tmX1st, px1, 2048, 640, 64, 80, CU_TENSOR_MAP_SWIZZLE_128B, XCP);
        make_tmap(&h_tmW.q, d_in[1], 16, 640, 16, 32, CU_TENSOR_MAP_SWIZZLE_32B, 1920, 16, 5);
        make_tmap(&h_tmW.o, d_in[2], 640, 640, 4, 0, CU_TENSOR_MAP_SWIZZLE_32B);
        make_tmap(&h_tmW.t, d_in[2], 640, 640, 2, 0, CU_TENSOR_MAP_SWIZZLE_32B);
        make_tmap(&h_tmOut, d_out, 640, 1024, 80, 8, CU_TENSOR_MAP_SWIZZLE_NONE, 1280, 640, 1);
        p_in = d_in[0]; p_w1 = d_in[1]; p_w2 = d_in[2]; p_out = d_out;
    }
    for (int k = 0; k < n_stage_kernels(); k++) launch_stage(k, d_in, d_out);
}
```

```cpp
#include <cuda_runtime.h>
#include <cuda_bf16.h>
#include <cuda_fp16.h>
#include <stdint.h>
#include <cuda.h>

typedef __nv_bfloat16 bf16;

constexpr int SEQ = 2048;
constexpr int DM = 640;
constexpr int NMODE = 192;

__device__ __forceinline__ float bf2f(bf16 v) { return __bfloat162float(v); }
__device__ __forceinline__ float rbf(float v) {
    uint32_t r;
    asm("cvt.rn.bf16x2.f32 %0, %1, %2;" : "=r"(r) : "f"(v), "f"(0.f));
    return __uint_as_float(r);
}
__device__ __forceinline__ uint32_t pack2(float lo, float hi) {
    __nv_bfloat162 t = __floats2bfloat162_rn(lo, hi);
    return *reinterpret_cast<uint32_t*>(&t);
}
__device__ __forceinline__ void pdl_sync() {
    asm volatile("griddepcontrol.wait;" ::: "memory");
    asm volatile("griddepcontrol.launch_dependents;" ::: "memory");
}
__device__ __forceinline__ float sqrt_apx(float v) { float r; asm("sqrt.approx.ftz.f32 %0, %1;" : "=f"(r) : "f"(v)); return r; }
__device__ __forceinline__ float rcp_apx(float v) { float r; asm("rcp.approx.ftz.f32 %0, %1;" : "=f"(r) : "f"(v)); return r; }
__device__ __forceinline__ uint32_t smem_u32(const void* p) { return (uint32_t)__cvta_generic_to_shared(p); }

constexpr int TAPB = 2944, TAPE = 928;
__device__ __align__(128) uint4 g_tap[DM * TAPB / 16];
#define XPAD 64
constexpr int XCP = SEQ + XPAD;
__device__ __align__(128) bf16 g_x1T[DM * XCP];
__device__ __align__(128) bf16 g_xcT[DM * XCP];
__device__ __align__(128) uint4 g_of[128 * 1280];
constexpr int WQ_STAGE = 240 * 128, WOB = 80 * 160;
__device__ __align__(128) uint4 g_wq[8 * 10 * WQ_STAGE / 16];
__device__ __align__(128) uint4 g_wo[64 * WOB / 16];
__device__ __align__(128) uint4 g_xb[128 * 240];
__device__ __align__(16) float g_csp[10 * 1920];
#define FSTR 32
__device__ __align__(128) float2 g_sum[2 * SEQ + 256 * FSTR];
__device__ __align__(16) bf16 g_piv[2 * SEQ];
__device__ __align__(128) bf16 g_yT[DM * XCP];
__device__ uint32_t g_epoch;
__device__ __align__(16) unsigned long long g_rstat[SEQ];
__device__ __align__(128) uint4 g_halo[640 * 148];
__device__ __forceinline__ unsigned long long tagw(uint32_t payload, uint32_t tag) { return ((unsigned long long)tag << 32) | payload; }
__device__ __forceinline__ ulonglong2 ld_tag2(const ulonglong2* p) {
    ulonglong2 v;
    asm volatile("ld.relaxed.gpu.global.v2.u64 {%0, %1}, [%2];" : "=l"(v.x), "=l"(v.y) : "l"(p) : "memory");
    return v;
}
__device__ __forceinline__ bool tag_ok(ulonglong2 v, uint32_t tag) { return (uint32_t)(v.x >> 32) == tag && (uint32_t)(v.y >> 32) == tag; }
__device__ __forceinline__ uint32_t ld_epoch() { uint32_t v; asm volatile("ld.relaxed.gpu.global.u32 %0, [%1];" : "=r"(v) : "l"(&g_epoch) : "memory"); return v + 1; }
constexpr int SPIN_MAX = 1 << 20;
__device__ __align__(128) uint32_t g_started[11 * 32];
__device__ __forceinline__ void sm_started(int slot) { asm volatile("red.relaxed.gpu.global.add.u32 [%0], 1;" ::"l"(g_started + slot) : "memory"); }
__device__ __forceinline__ void publish(int slot) {
    asm volatile("fence.proxy.async.global;" ::: "memory");
    asm volatile("red.release.gpu.global.add.u32 [%0], 1;" ::"l"(g_started + slot) : "memory");
}
__device__ __forceinline__ void await_all(int slot, uint32_t want) {
#pragma unroll 1
    for (int it = 0; it < SPIN_MAX; it++) {
        uint32_t v;
        asm volatile("ld.acquire.gpu.global.u32 %0, [%1];" : "=r"(v) : "l"(g_started + slot) : "memory");
        if (__all_sync(~0u, (int)(v - want) >= 0)) break;
        __nanosleep(50);
    }
    asm volatile("fence.proxy.async.global;" ::: "memory");
}
__device__ __noinline__ void sm_idle(int slot) {
    if (threadIdx.x != 288) return;
    asm volatile("fence.acq_rel.gpu;" ::: "memory");
    asm volatile("fence.proxy.async.global;" ::: "memory");
    sm_started(slot);
    const uint32_t want = ld_epoch() * gridDim.x;
    pdl_sync();
#pragma unroll 1
    for (int it = 0; it < SPIN_MAX; it++) {
        uint32_t v;
        asm volatile("ld.relaxed.gpu.global.u32 %0, [%1];" : "=r"(v) : "l"(g_started + slot) : "memory");
        if ((int)(v - want) >= 0) break;
        __nanosleep(100);
    }
}
struct TileTab { uint4 e[132]; };
__device__ __forceinline__ bool elect() {
    uint32_t p;
    asm volatile("{\n.reg .pred p;\nelect.sync _|p, 0xffffffff;\nselp.b32 %0, 1, 0, p;\n}" : "=r"(p));
    return p;
}
#define DBG_SYMS
#define TSTAMP(i)
#define TSTAMP1(i)
#define TSTAMP1T(i, t)
#define TSTAMP1X(i, t)
#define SPAN(k, i)
#define GSTAMP(arr, i)
#define TSTAMP2(i)
#define TSTAMP3(i)
#define TSTAMP4(i)
#define TSTAMPK(i, t)
#define TSTAMPC(i)
#define DBGC(i)
#define DBGV(i, v)
#define DBGCAL(i)

#define CSK(i)
#define CSK_END
#define CSA(i)
#define CSA_END
#define CST(i)
#define CST_END
#define CST_EXTRA 0
__device__ __forceinline__ void mma_bf16(float* d, uint32_t a0, uint32_t a1, uint32_t a2, uint32_t a3, uint32_t b0, uint32_t b1) {
    asm volatile("mma.sync.aligned.m16n8k16.row.col.f32.bf16.bf16.f32 {%0,%1,%2,%3}, {%4,%5,%6,%7}, {%8,%9}, {%0,%1,%2,%3};"
                 : "+f"(d[0]), "+f"(d[1]), "+f"(d[2]), "+f"(d[3]) : "r"(a0), "r"(a1), "r"(a2), "r"(a3), "r"(b0), "r"(b1));
}
__device__ __forceinline__ void mma_bf16_k8(float* d, uint32_t a0, uint32_t a1, uint32_t b0) {
    asm volatile("mma.sync.aligned.m16n8k8.row.col.f32.bf16.bf16.f32 {%0,%1,%2,%3}, {%4,%5}, {%6}, {%0,%1,%2,%3};"
                 : "+f"(d[0]), "+f"(d[1]), "+f"(d[2]), "+f"(d[3]) : "r"(a0), "r"(a1), "r"(b0));
}
__device__ __forceinline__ void ldsm_x4(uint32_t* r, uint32_t addr) {
    asm volatile("ldmatrix.sync.aligned.m8n8.x4.shared.b16 {%0,%1,%2,%3}, [%4];"
                 : "=r"(r[0]), "=r"(r[1]), "=r"(r[2]), "=r"(r[3]) : "r"(addr));
}

__device__ __forceinline__ void ldsm_x4_t(uint32_t* r, uint32_t addr) {
    asm volatile("ldmatrix.sync.aligned.m8n8.x4.trans.shared.b16 {%0,%1,%2,%3}, [%4];"
                 : "=r"(r[0]), "=r"(r[1]), "=r"(r[2]), "=r"(r[3]) : "r"(addr));
}
__device__ __forceinline__ void mbar_init(uint32_t bar, int count) { asm volatile("mbarrier.init.shared::cta.b64 [%0], %1;" ::"r"(bar), "r"(count)); }
__device__ __forceinline__ void mbar_arrive(uint32_t bar) { asm volatile("mbarrier.arrive.shared::cta.b64 _, [%0];" ::"r"(bar) : "memory"); }
__device__ __forceinline__ void mbar_wait(uint32_t bar, uint32_t parity) {
    asm volatile("{\n.reg .pred p;\nWAIT_LOOP:\n"
                 "mbarrier.try_wait.parity.shared::cta.b64 p, [%0], %1;\n"
                 "@p bra.uni WAIT_DONE;\nbra.uni WAIT_LOOP;\nWAIT_DONE:\n}" ::"r"(bar), "r"(parity) : "memory");
}

__device__ __forceinline__ void mbar_expect_tx(uint32_t bar, uint32_t bytes) {
    asm volatile("mbarrier.arrive.expect_tx.shared::cta.b64 _, [%0], %1;" ::"r"(bar), "r"(bytes) : "memory");
}
__device__ __forceinline__ void tma_load_2d(uint32_t dst, const void* tmap, int c0, int c1, uint32_t bar) {
    asm volatile("cp.async.bulk.tensor.2d.shared::cluster.global.mbarrier::complete_tx::bytes [%0], [%1, {%3, %4}], [%2];"
                 ::"r"(dst), "l"(tmap), "r"(bar), "r"(c0), "r"(c1) : "memory");
}
__device__ __forceinline__ void tma_load_3d(uint32_t dst, const void* tmap, int c0, int c1, int c2, uint32_t bar) {
    asm volatile("cp.async.bulk.tensor.3d.shared::cluster.global.mbarrier::complete_tx::bytes [%0], [%1, {%3, %4, %5}], [%2];"
                 ::"r"(dst), "l"(tmap), "r"(bar), "r"(c0), "r"(c1), "r"(c2) : "memory");
}
__device__ __forceinline__ void fence_async_smem() { asm volatile("fence.proxy.async.shared::cta;" ::: "memory"); }
__device__ __forceinline__ void bulk_load(uint32_t dst, const void* src, uint32_t bytes, uint32_t bar) {
    asm volatile("cp.async.bulk.shared::cluster.global.mbarrier::complete_tx::bytes [%0], [%1], %2, [%3];"
                 ::"r"(dst), "l"(src), "r"(bytes), "r"(bar) : "memory");
}
__device__ __forceinline__ void stsm_x4(uint32_t addr, uint32_t r0, uint32_t r1, uint32_t r2, uint32_t r3) {
    asm volatile("stmatrix.sync.aligned.m8n8.x4.shared.b16 [%0], {%1,%2,%3,%4};" ::"r"(addr), "r"(r0), "r"(r1), "r"(r2), "r"(r3) : "memory");
}
__device__ __forceinline__ void stsm_x4_t(uint32_t addr, uint32_t r0, uint32_t r1, uint32_t r2, uint32_t r3) {
    asm volatile("stmatrix.sync.aligned.m8n8.x4.trans.shared.b16 [%0], {%1,%2,%3,%4};" ::"r"(addr), "r"(r0), "r"(r1), "r"(r2), "r"(r3) : "memory");
}
__device__ __forceinline__ void prefetch_tmap(const void* tmap) { asm volatile("prefetch.tensormap [%0];" ::"l"(tmap) : "memory"); }

__device__ __forceinline__ float2 cexp_at(float wr2, float wi, float p) {
    float er;
    asm("ex2.approx.ftz.f32 %0, %1;" : "=f"(er) : "f"(wr2 * p));
    float th = wi * p;
    const float k = rintf(th * 0.15915494309189535f);
    th = fmaf(k, -6.2831854820251465f, th);
    th = fmaf(k, 1.7484555314695172e-7f, th);
    return make_float2(er * __cosf(th), er * __sinf(th));
}
__device__ __forceinline__ float2 cmul(float2 a, float2 b) {
    return make_float2(fmaf(a.x, b.x, -a.y * b.y), fmaf(a.x, b.y, a.y * b.x));
}
__device__ __forceinline__ float2 csqr(float2 a) { return make_float2(fmaf(a.x, a.x, -a.y * a.y), (a.x + a.x) * a.y); }
__device__ __forceinline__ uint32_t packh(float2 v) {
    uint32_t r;
    asm("cvt.rn.f16x2.f32 %0, %1, %2;" : "=r"(r) : "f"(v.y), "f"(v.x));
    return r;
}
__device__ __forceinline__ uint2 packr(float2 v) { return make_uint2(packh(v), packh(make_float2(-v.y, v.x))); }
__device__ __forceinline__ uint32_t hcmul(uint32_t a, uint2 b) {
    const __half2 x = *reinterpret_cast<const __half2*>(&a);
    const __half2 r = __hfma2(__high2half2(x), *reinterpret_cast<const __half2*>(&b.y), __hmul2(__low2half2(x), *reinterpret_cast<const __half2*>(&b.x)));
    return *reinterpret_cast<const uint32_t*>(&r);
}

struct Par { const bf16 *logA, *Aim, *Cre, *Cim, *logdt, *dsk; int layer, pad; const bf16* x; uint4 *sum, *wop, *of, *halo, *tap; float* csp; uint4* wq; const bf16 *wqkv, *wo; };
struct KgMaps { CUtensorMap q, o, t; };

__device__ __forceinline__ void bulk_prefetch(const void* p, uint32_t bytes) { asm volatile("cp.async.bulk.prefetch.L2.global [%0], %1;" ::"l"(p), "r"(bytes) : "memory"); }
__device__ __forceinline__ void bulk_store(void* dst, uint32_t src, uint32_t bytes) { asm volatile("cp.async.bulk.global.shared::cta.bulk_group [%0], [%1], %2;" ::"l"(dst), "r"(src), "r"(bytes) : "memory"); }
__device__ __forceinline__ void kgen_first(const Par& in, const KgMaps& tm, const uint32_t b0, const uint32_t wbar, const bool one) {
    const uint32_t blk = blockIdx.x, sec = (blk >= 40) + (blk >= 80), it = (blk >> 3) - 5 * sec, up = (blk >> 2) & 1, hi = blk >> 6;
    auto fetch = [&](int h) {
        if (blk < 120) asm volatile("cp.async.bulk.tensor.4d.shared::cluster.global.mbarrier::complete_tx::bytes [%0], [%1, {%3, %3, %4, %5}], [%2];"
                                    ::"r"(b0 + 10240 * h), "l"(&tm.q), "r"(wbar + 8 * h), "r"(0), "r"(sec * 40 + (blk & 7) * 5), "r"(2 * it + 10 * (up ^ h)) : "memory");
    };
    auto fetch_o = [&](int i) {
        asm volatile("cp.async.bulk.tensor.5d.shared::cluster.global.mbarrier::complete_tx::bytes [%0], [%1, {%3, %3, %4, %3, %5}], [%2];"
                     ::"r"(b0 + 20480 + i * 5120), "l"(&tm.o + i), "r"(wbar + 16), "r"(0), "r"((blk & 7) * 10 + (hi + i) * 4), "r"(((blk >> 3) & 7) * 5) : "memory");
    };
    if (one) {
#pragma unroll
        for (int i = 0; i < 3; i++) mbar_init(wbar + 8 * i, 1);
        asm volatile("fence.mbarrier_init.release.cluster;" ::: "memory");
        fetch(0);
    }
    __syncwarp();
    if (blk >> 20) __trap();
    if (one) {
        bulk_prefetch(in.wqkv + blk * 9600, 19200);
        fetch(1);
        bulk_prefetch(in.wo + blk * 3200, 6400);
        fetch_o(0);
        if (hi) fetch_o(1);
        mbar_expect_tx(wbar, 10240); mbar_expect_tx(wbar + 8, 10240); mbar_expect_tx(wbar + 16, 5120 + hi * 2560);
        bulk_prefetch(in.x + blk * 10240, 20480);
    }
}
__device__ __forceinline__ void kgen_side(const Par& in, const uint32_t b0, const uint32_t wbar) {
    const uint32_t blk = blockIdx.x, sec = (blk >= 40) + (blk >= 80), it = (blk >> 3) - 5 * sec, cg = (blk >> 3) & 7, hb = blk & 7;
    unsigned char* dst = reinterpret_cast<unsigned char*>(in.wq) + (hb * 10 + it) * WQ_STAGE + sec * 5120;
    if (blk < 120) {
        mbar_wait(wbar, 0);
        CSK(2);
        bulk_store(dst, b0, 5120); bulk_store(dst + 15360, b0 + 5120, 5120);
        mbar_wait(wbar + 8, 0);
        CSK(3);
        bulk_store(dst + 5 * WQ_STAGE, b0 + 10240, 5120); bulk_store(dst + 5 * WQ_STAGE + 15360, b0 + 15360, 5120);
        asm volatile("cp.async.bulk.commit_group;" ::: "memory");
        asm volatile("cp.async.bulk.wait_group 0;" ::: "memory");
        CSK(4);
        publish(96 + 32 * hb);
        CSK(5);
    }
    if (blk < 128) {
        mbar_wait(wbar + 16, 0);
        bulk_store(reinterpret_cast<unsigned char*>(in.wop) + (cg * 8 + (hb == cg ? 0 : hb + (hb < cg))) * WOB + (blk >> 6) * 5120, b0 + 20480, blk < 64 ? 5120 : 7680);
        asm volatile("cp.async.bulk.commit_group;" ::: "memory");
    }
}
__device__ __forceinline__ void kgen_sums(const Par& in, const uint32_t b0, const int h) {
    const int lane = threadIdx.x & 31, blk = blockIdx.x;
    if (blk < 120) {
        float cs[5][4] = {};
#pragma unroll
        for (int a = 0; a < 4; a++)
#pragma unroll
            for (int j = 0; j < 5; j++) {
                uint32_t w[4];
                ldsm_x4_t(w, b0 + h * 10240 + j * 1024 + ((lane >> 4) * 8 + (lane & 7)) * 32 + ((((lane >> 3) ^ (lane >> 2)) & 1) << 4) + (a >> 1) * 5120 + (a & 1) * 512);
                mma_bf16(cs[j], w[0], w[1], w[2], w[3], 0x3f803f80u, 0x3f803f80u);
            }
#pragma unroll
        for (int j = 0; j < 5; j++)
            if ((lane & 3) < 2) in.csp[(blk + 120 * h) * 80 + j * 16 + (lane >> 2) + 8 * (lane & 3)] = (lane & 3) ? cs[j][2] : cs[j][0];
    }
}
struct KgPar { uint32_t pw[4], ph[4], pdt, pdsk; };
__device__ __forceinline__ void kgen_load(const Par& in, const bf16* logA, const int w11, KgPar& k) {
    const uint32_t o = blockIdx.x * 480 + min(w11 * 48, w11 * 32 + 128), ow = o + (threadIdx.x & 31), oh = o + ow + (w11 < 8 ? 64 : 0);
    k.pdt = reinterpret_cast<const unsigned short*>(in.logdt)[ow / 96];
    k.pdsk = reinterpret_cast<const unsigned short*>(in.dsk)[ow / 96];
#pragma unroll
    for (int i = 0; i < 4; i++) {
        const bf16* p = i == 0 ? logA : i == 1 ? in.Aim : i == 2 ? in.Cre : in.Cim;
        k.pw[i] = reinterpret_cast<const uint32_t*>(p)[ow]; k.ph[i] = reinterpret_cast<const unsigned short*>(p)[oh];
    }
}
__device__ __forceinline__ void kgen_tables(const Par& in, uint4* tabs, const int w11, const KgPar& kp) {
    const int lane = threadIdx.x & 31, grp = min(w11 >> 1, 4), warp = w11 - 2 * grp;
    const int blk = blockIdx.x, d = blk * 5 + grp, tid = warp * 32 + lane;
    uint4* tab = tabs + grp * (2 * 256);
    const uint32_t *pw = kp.pw, *ph = kp.ph;
#pragma unroll
    for (int i = 0; i < 3; i++)
        if (i < 2 || w11 * 32 + lane < 36) asm volatile("st.global.v4.u32 [%0], {%1,%1,%1,%1};" ::"l"(in.halo + blk * 740 + w11 * 32 + lane + 352 * i), "r"(~0u));
    __syncwarp();
    if (w11 == 10) {
        if (lane < 16) in.sum[blk * 16 + lane] = make_uint4(0, 0, 0, 0);
        else if (lane < 20) reinterpret_cast<uint32_t*>(in.sum + 2048)[(blk * 4 + lane - 16) * FSTR] = 0;
    } else if (w11 > 1) asm volatile("bar.arrive 9, 352;" ::: "memory");
#pragma unroll
    for (int i = 0; i < 6; i++) tabs[w11 * 256 + 32 * i + lane] = make_uint4(0, 0, 0, 0);
    __syncwarp();
    CSK(1);
    const uint32_t tw = smem_u32(tabs) + w11 * 4096;
    const int g = lane >> 2, t = lane & 3;
    const int mt = lane >> 3, r = lane & 7;
    const uint32_t st1 = tw + mt * 1024 + r * 16, st2 = tw + (mt & 1) * 1024 + (mt >> 1) * 128 + ((r ^ (mt >> 1)) << 4), st3 = tw + 2048 + mt * 128 + ((r ^ mt) << 4);
    const uint32_t lda = tw + (mt & 1) * 1024 + r * 128 + (((mt >> 1) ^ r) << 4), ldb = tw + (mt >> 1) * 1024 + r * 128 + (((mt & 1) ^ r) << 4), ldc = tw + 2048 + r * 128 + ((mt ^ r) << 4);
    auto ldsm = [](uint32_t* v, uint32_t a) {
        asm volatile("ldmatrix.sync.aligned.m8n8.x4.shared.b16 {%0,%1,%2,%3}, [%4];" : "=r"(v[0]), "=r"(v[1]), "=r"(v[2]), "=r"(v[3]) : "r"(a) : "memory");
    };
    auto mma = [](float* c, const uint32_t* a, const uint32_t* b) {
        asm("mma.sync.aligned.m16n8k16.row.col.f32.f16.f16.f32 {%0,%1,%2,%3}, {%4,%5,%6,%7}, {%8,%9}, {%0,%1,%2,%3};"
            : "+f"(c[0]), "+f"(c[1]), "+f"(c[2]), "+f"(c[3]) : "r"(a[0]), "r"(a[1]), "r"(a[2]), "r"(a[3]), "r"(b[0]), "r"(b[1]));
    };
    asm volatile("st.shared.u32 [%0], %1;" ::"r"(tw + 3072), "r"(st1 ^ st2 ^ st3 ^ lda ^ ldb ^ ldc) : "memory");
    if (in.pad) __trap();
    const float dt = rbf(expf(__uint_as_float(kp.pdt << 16)));
    const uint32_t cm = __vmaxu2(__vmaxu2(pw[2] & 0x7fff7fffu, pw[3] & 0x7fff7fffu), __byte_perm(ph[2], ph[3], 0x5410) & 0x7fff7fffu);
    const int ex = min(max((int)(__float_as_uint(__uint_as_float(__reduce_max_sync(~0u, max(cm << 16, cm & 0xffff0000u))) * dt) >> 23), 20), 240);
    const float scale = __uint_as_float((uint32_t)(127 + 10 + 127 - ex) << 23), unscale = 2.0f * __uint_as_float((uint32_t)(ex - 10) << 23);
    float k2048 = 0.f;
    float acc[5][4] = {};
    uint32_t af[4][4] = {};
    auto rest = [&] {
        uint32_t b[4][4], c[8];
#pragma unroll
        for (int k = 0; k < 4; k++) {
            ldsm(b[k], ldb ^ (k << 5));
            if (!(k & 1)) ldsm(c + 2 * k, ldc ^ (k << 5));
        }
#pragma unroll
        for (int k = 0; k < 4; k++) { mma(acc[2], af[k], b[k]); mma(acc[3], af[k], b[k] + 2); mma(acc[4], af[k], c + 2 * k); }
    };
#pragma unroll 1
    for (uint32_t sel = 0x1076; sel < (grp < 4 ? 0x6000u : 0x4000u); sel += 0x2200) {
        rest();
        auto par = [&](int i) { return __uint_as_float(__byte_perm(pw[i], ph[i], sel)); };
        const float wr2 = -rbf(expf(par(0))) * dt * 1.4426950408889634f, wi = par(1) * dt;
        const float2 y1 = cexp_at(wr2, -wi, 1.f), w64 = cexp_at(wr2, wi, 64.f), y4 = csqr(csqr(y1)), z8 = csqr(make_float2(y4.x, -y4.y)), y128 = csqr(make_float2(w64.x, -w64.y));
        float2 h0 = make_float2(1.f, 0.f), g0 = make_float2(par(2) * dt * scale, -par(3) * dt * scale);
        const float2 v2 = csqr(y128), v3 = cmul(v2, y128), v4 = csqr(v2), v8 = csqr(v4), c8 = cmul(g0, v8);
        const uint2 z64 = packr(w64), v[8] = {make_uint2(packh(c8), 0u), packr(y128), packr(v2), packr(v3), packr(v4), packr(cmul(v4, y128)), packr(csqr(v3)), packr(cmul(v4, v3))};
        k2048 += fmaf(c8.x, v8.x, -c8.y * v8.y);
        uint32_t ge[4];
#pragma unroll
        for (int e = 0; e < 8; e++) {
            const uint32_t p = packh(h0), q = packh(g0);
            if (!(e & 1)) ge[e >> 1] = q;
            stsm_x4((st1 ^ (e << 4)) + e * 128, p, e ? hcmul(p, z64) : z64.x, q, hcmul(q, v[1]));
            if (e < 7) { h0 = e ? cmul(h0, z8) : z8; g0 = cmul(g0, y1); }
        }
        __syncwarp();
        uint32_t b[4][4];
#pragma unroll
        for (int k = 0; k < 4; k++) { ldsm(af[k], lda ^ (k << 5)); ldsm(b[k], (ldb ^ (k << 5)) + 2048); }
#pragma unroll
        for (int e = 0; e < 8; e += 2) {
            stsm_x4((st2 ^ (e << 4)) + e * 128, hcmul(ge[e & 3], v[2 + (e >> 2)]), hcmul(ge[0], v[4 + (e >> 1)]), hcmul(ge[(e & 3) + 1], v[2 + (e >> 2)]), hcmul(ge[2], v[4 + (e >> 1)]));
            if (!(e & 3)) stsm_x4((st3 ^ (e << 4)) + e * 128, e ? hcmul(v[0].x, v[e]) : v[0].x, hcmul(v[0].x, v[e + 1]), hcmul(v[0].x, v[e + 2]), hcmul(v[0].x, v[e + 3]));
            mma(acc[0], af[e >> 1], b[e >> 1]);
            mma(acc[1], af[e >> 1], b[e >> 1] + 2);
        }
        __syncwarp();
        if (sel == 0x1076) CSK(3);
    }
    rest();
#pragma unroll
    for (int e = 0; e < 5; e++) k2048 += __shfl_xor_sync(~0u, k2048, 1 << e);
    {
        float* Pp = reinterpret_cast<float*>(tab + warp * 256);
        auto sw = [](int i) { return i ^ ((i >> 2) & 24); };
#pragma unroll
        for (int h = 0; h < 2; h++) {
            const int b = g + 8 * h;
            *reinterpret_cast<float2*>(Pp + sw(8 * b + 2 * t)) = make_float2(acc[0][2 * h] * unscale, acc[0][2 * h + 1] * unscale);
            *reinterpret_cast<float2*>(Pp + 128 + sw(8 * b + 2 * t)) = make_float2(acc[1][2 * h] * unscale, acc[1][2 * h + 1] * unscale);
            *reinterpret_cast<float2*>(Pp + 256 + sw(4 * b + 2 * (t & 1) + 64 * (t >> 1))) = make_float2(acc[2][2 * h] * unscale, acc[2][2 * h + 1] * unscale);
            *reinterpret_cast<float2*>(Pp + 384 + sw(2 * b + 32 * t)) = make_float2(acc[3][2 * h] * unscale, acc[3][2 * h + 1] * unscale);
            Pp[512 + sw(b + 32 * t)] = acc[4][2 * h] * unscale;
            Pp[512 + sw(b + 32 * t + 16)] = acc[4][2 * h + 1] * unscale;
        }
        if (lane == 0) Pp[640] = k2048 * unscale;
    }
    CSK(4);
    asm volatile("bar.sync %0, %1;" ::"r"(grp + 4), "r"(grp < 4 ? 64 : 96) : "memory");
    if (warp == 2) return;
    const float* Kp = reinterpret_cast<const float*>(tab);
    auto ksum = [&](int i) -> float { return rbf(Kp[i] + Kp[1024 + i] + (grp < 4 ? 0.f : Kp[2048 + i])); };
    auto ksum2 = [&](int q) -> float2 {
        q ^= (q >> 2) & 12;
        const float2 a = reinterpret_cast<const float2*>(Kp)[q], b = reinterpret_cast<const float2*>(Kp)[512 + q];
        const float2 c = grp < 4 ? make_float2(0.f, 0.f) : reinterpret_cast<const float2*>(Kp)[1024 + q];
        return make_float2(a.x + b.x + c.x, a.y + b.y + c.y);
    };
    {
        uint2* W2 = reinterpret_cast<uint2*>(in.tap + d * (TAPB / 16)) + 8;
        uint2* E4 = W2 + (TAPE - 64) / 8;
        float2 v = ksum2(64 * warp + lane), z = ksum2(64 * warp + 32 + lane), y = ksum2(128 + tid);
        const int q = (96 + tid) ^ (((96 + tid) >> 2) & 6);
        const float4 ua = reinterpret_cast<const float4*>(Kp)[q], uc = reinterpret_cast<const float4*>(Kp)[256 + q], ud = grp < 4 ? make_float4(0.f, 0.f, 0.f, 0.f) : reinterpret_cast<const float4*>(Kp)[512 + q];
        const float4 ub = make_float4(uc.x + ud.x, uc.y + ud.y, uc.z + ud.z, uc.w + ud.w);
        const float s1 = ksum(tid == 31 ? 336 : lane ? 384 : 103), s2 = ksum(tid == 31 ? 512 : tid ? 640 : 231);
        if (tid == 0) v.x += __uint_as_float(kp.pdsk << 16);
        if (tid == 63) y.y -= s1;
        const uint32_t lo = pack2(v.x, v.y), hi = pack2(z.x, z.y), tp = pack2(y.x, y.y);
        uint32_t nl = __shfl_sync(~0u, lo, lane - 1), nh = __shfl_sync(~0u, lane == 31 ? lo : hi, lane - 1), nt = __shfl_sync(~0u, tp, lane + 1);
        if (lane == 0) nl = warp ? __float_as_uint(s1) : 0u;
        if (lane == 31) nt = warp ? 0u : __float_as_uint(s1) >> 16;
        W2[64 * warp + lane] = make_uint2(__byte_perm(lo, nl, 0x7610), __byte_perm(lo, 0, 0x1032));
        W2[64 * warp + lane + 32] = make_uint2(__byte_perm(hi, nh, 0x7610), __byte_perm(hi, 0, 0x1032));
        reinterpret_cast<uint4*>(W2)[64 + tid] = make_uint4(__byte_perm(tp, __float_as_uint(s2), tid ? 0x1010 : 0x7610), __byte_perm(tp, 0, 0x1010), __byte_perm(tp, 0, 0x1032), __byte_perm(nt, tp, 0x7610));
        E4[(tid < 32 ? 159 : 209 - 32) + tid] = make_uint2(pack2(ua.x + ub.x, ua.y + ub.y), pack2(ua.z + ub.z, ua.w + ub.w - (tid == 31 ? s2 : 0.f)));
        if (tid == 63) E4[241] = make_uint2(__float_as_uint(s2) >> 16, 0u);
    }
    CSK(5);
    SPAN(0, 3);
}

#define CV_SLEEP 40
#define CV_LD "ld.relaxed.gpu.global"
#define CV_NL 1
#define CV_D2 3
#define CV_PDH 12
#define CV_PDF 4
#define CV_HAND 7
constexpr int CV_CPB = 5;
constexpr int CV_THREADS = 512;
constexpr int UPADF = 128;
constexpr int ULEN = UPADF + SEQ;
constexpr int XLEN = XCP;
constexpr int BX_5 = 0, BX_3 = 3264, BX_9 = 6528, BX_7 = 8960, BX_LEN = 11392;
constexpr int CV_SM_U = 0;
constexpr int CV_SM_T = CV_CPB * ULEN * 2;
constexpr int CV_SM_B = CV_SM_T + CV_CPB * TAPB;
constexpr int CV_SM_X = CV_SM_B + CV_CPB * BX_LEN;
constexpr int CV_SM_Y = (CV_SM_X + CV_CPB * XLEN * 2 + 127) & ~127;
constexpr int CV_SM_CNT = CV_SM_Y + CV_CPB * 8192;
constexpr int CV_SM_O = CV_SM_CNT + 128;
constexpr int CV_SMEM = CV_SM_O + 20480 + CST_EXTRA;
static_assert(ULEN % 128 == 0 && CV_SM_B % 128 == 0 && CV_SM_CNT % 128 == 0, "layout");

__device__ __forceinline__ uint32_t sub2(uint32_t x, uint32_t m) {
    const __nv_bfloat162 d = __hsub2(*reinterpret_cast<const __nv_bfloat162*>(&x), *reinterpret_cast<const __nv_bfloat162*>(&m));
    return *reinterpret_cast<const uint32_t*>(&d);
}
__device__ __forceinline__ uint32_t add2(uint32_t x, uint32_t y) {
    const __nv_bfloat162 d = __hadd2_rn(*reinterpret_cast<const __nv_bfloat162*>(&x), *reinterpret_cast<const __nv_bfloat162*>(&y));
    return *reinterpret_cast<const uint32_t*>(&d);
}
__device__ __forceinline__ void wgmma_fence() { asm volatile("wgmma.fence.sync.aligned;" ::: "memory"); }
__device__ __forceinline__ void wgmma_commit() { asm volatile("wgmma.commit_group.sync.aligned;" ::: "memory"); }
template <int N> __device__ __forceinline__ void wgmma_wait() { asm volatile("wgmma.wait_group.sync.aligned %0;" ::"n"(N) : "memory"); }
__device__ __forceinline__ uint64_t make_desc(uint32_t addr, uint32_t lbo, uint32_t sbo, uint32_t mode) {
    return (uint64_t)((addr & 0x3FFFF) >> 4) | ((uint64_t)(lbo >> 4) << 16) | ((uint64_t)(sbo >> 4) << 32) | ((uint64_t)mode << 62);
}
__device__ __forceinline__ void wgmma_rs128(float (&d)[64], uint2 hi, uint2 lo, uint64_t db, int acc) {
    asm volatile("{\n.reg .pred p;\nsetp.ne.b32 p, %69, 0;\nwgmma.mma_async.sync.aligned.m64n128k16.f32.bf16.bf16 {%0,%1,%2,%3,%4,%5,%6,%7,%8,%9,%10,%11,%12,%13,%14,%15,%16,%17,%18,%19,%20,%21,%22,%23,%24,%25,%26,%27,%28,%29,%30,%31,%32,%33,%34,%35,%36,%37,%38,%39,%40,%41,%42,%43,%44,%45,%46,%47,%48,%49,%50,%51,%52,%53,%54,%55,%56,%57,%58,%59,%60,%61,%62,%63}, {%64,%65,%66,%67}, %68, p, 1, 1, 0;\n}"
                 : "+f"(d[0]), "+f"(d[1]), "+f"(d[2]), "+f"(d[3]), "+f"(d[4]), "+f"(d[5]), "+f"(d[6]), "+f"(d[7]), "+f"(d[8]), "+f"(d[9]), "+f"(d[10]), "+f"(d[11]), "+f"(d[12]), "+f"(d[13]), "+f"(d[14]), "+f"(d[15]), "+f"(d[16]), "+f"(d[17]), "+f"(d[18]), "+f"(d[19]), "+f"(d[20]), "+f"(d[21]), "+f"(d[22]), "+f"(d[23]), "+f"(d[24]), "+f"(d[25]), "+f"(d[26]), "+f"(d[27]), "+f"(d[28]), "+f"(d[29]), "+f"(d[30]), "+f"(d[31]), "+f"(d[32]), "+f"(d[33]), "+f"(d[34]), "+f"(d[35]), "+f"(d[36]), "+f"(d[37]), "+f"(d[38]), "+f"(d[39]), "+f"(d[40]), "+f"(d[41]), "+f"(d[42]), "+f"(d[43]), "+f"(d[44]), "+f"(d[45]), "+f"(d[46]), "+f"(d[47]), "+f"(d[48]), "+f"(d[49]), "+f"(d[50]), "+f"(d[51]), "+f"(d[52]), "+f"(d[53]), "+f"(d[54]), "+f"(d[55]), "+f"(d[56]), "+f"(d[57]), "+f"(d[58]), "+f"(d[59]), "+f"(d[60]), "+f"(d[61]), "+f"(d[62]), "+f"(d[63])
                 : "r"(hi.x), "r"(hi.y), "r"(lo.x), "r"(lo.y), "l"(db), "r"(acc));
}
template <int V> struct Int { __device__ constexpr operator int() const { return V; } };
__device__ __forceinline__ void sts4(uint32_t a, const uint32_t* v) { asm volatile("st.shared.v4.u32 [%0], {%1,%2,%3,%4};" ::"r"(a), "r"(v[0]), "r"(v[1]), "r"(v[2]), "r"(v[3]) : "memory"); }
__device__ __forceinline__ uint32_t lds1(uint32_t a) { uint32_t v; asm volatile("ld.shared.u32 %0, [%1];" : "=r"(v) : "r"(a) : "memory"); return v; }
__device__ __forceinline__ uint32_t lds1v(uint32_t a) { uint32_t v; asm volatile("ld.volatile.shared.u32 %0, [%1];" : "=r"(v) : "r"(a) : "memory"); return v; }
__device__ __forceinline__ uint4 lds4(uint32_t a) { uint4 v; asm volatile("ld.shared.v4.u32 {%0,%1,%2,%3}, [%4];" : "=r"(v.x), "=r"(v.y), "=r"(v.z), "=r"(v.w) : "r"(a) : "memory"); return v; }
__device__ __forceinline__ uint4 ldx(uint32_t a) {
    uint4 v;
    asm volatile("ld.shared.v2.u32 {%0,%1}, [%4];\nld.shared.v2.u32 {%2,%3}, [%4+128];" : "=r"(v.x), "=r"(v.y), "=r"(v.z), "=r"(v.w) : "r"(a) : "memory");
    return v;
}
__device__ __forceinline__ void cv_store(unsigned char* p, uint4 x, uint4 y) {
    asm volatile("st.relaxed.gpu.global.v2.u32 [%0], {%1,%2};" ::"l"(p), "r"(add2(x.x, __byte_perm(y.x, y.y, 0x5410))), "r"(add2(x.y, __byte_perm(y.z, y.w, 0x5410))) : "memory");
    asm volatile("st.relaxed.gpu.global.v2.u32 [%0], {%1,%2};" ::"l"(p + 128), "r"(add2(x.z, __byte_perm(y.x, y.y, 0x7632))), "r"(add2(x.w, __byte_perm(y.z, y.w, 0x7632))) : "memory");
}
__device__ __forceinline__ int usw(int ch) { return ch ^ ((ch >> 3) & 1); }
__global__ void __launch_bounds__(CV_THREADS, 1) conv_kernel(int layer, const uint4* __restrict__ piv, const float4* __restrict__ sum, const bf16* __restrict__ x1T,
                                                             bf16* __restrict__ dst, const uint4* __restrict__ tap, const __grid_constant__ CUtensorMap tmOut) {
    extern __shared__ __align__(1024) unsigned char sm[];
    SPAN(3 + 4 * layer, 0);
    bf16* Us = reinterpret_cast<bf16*>(sm + CV_SM_U);
    bf16* Xs = reinterpret_cast<bf16*>(sm + CV_SM_X);
#define CV_IDX int tid; asm volatile("mov.u32 %0, %tid.x;" : "=r"(tid)); const int lane = tid & 31, warp = __shfl_sync(~0u, tid >> 5, 0);
    const int d0 = blockIdx.x * CV_CPB, tile = blockIdx.x; (void)tile;
    const uint32_t cnt = smem_u32(sm + CV_SM_CNT);
    struct Lc { uint32_t a4, a8, uc, ud, y, e4, en, sp, ss; int go; };
    auto lane_consts = [&](int lane, int c) {
        const int mat = lane >> 3, r = lane & 7, g = lane >> 2, ti = lane & 3, e = g - 2 * ti;
        const int j2 = 13 + (r ^ 1) + 8 * (mat >> 1), j3 = j2 + 2, i0 = 8 * (mat & 1);
        const uint32_t sb = smem_u32(sm), oc = sb + usw(16 * (mat >> 1) + 2 * r + (mat & 1)) * 16;
        const Lc l = {sb + CV_SM_B + c * BX_LEN + ((j2 & 1) ? BX_3 + (4 * j2 + i0 + 84) * 2 : BX_5 + (4 * j2 + i0 + 80) * 2),
                      sb + CV_SM_B + c * BX_LEN + ((j3 & 1) ? BX_7 : BX_9) + (8 * j3 + i0 + 136) * 2,
                      oc + CV_SM_U + (c * ULEN + UPADF) * 2, sb + CV_SM_U + (c * ULEN + UPADF) * 2 + usw(16 * mat + 2 * r + 2) * 16, oc + CV_SM_Y + c * 8192,
                      sb + CV_SM_T + c * TAPB + TAPE + (307 + 2 * g - ti) * 4, sb + CV_SM_T + c * TAPB + (528 + e) * 4,
                      e == -5 ? 0x4410u : e == -4 ? 0x1044u : 0x4444u, e == 3 ? 0x4410u : e == 4 ? 0x1044u : 0x4444u,
                      c * XCP * 2 + (lane >> 4) * 256 + (lane & 15) * 8};
        asm volatile("st.shared.u32 [%0], %1;" ::"r"(sb + CV_SM_CNT + 120), "r"(l.y ^ l.a4 ^ l.a8 ^ l.uc ^ l.ud ^ l.e4 ^ l.en ^ l.sp ^ l.ss ^ l.go) : "memory");
        return l;
    };
    unsigned char* const dq = reinterpret_cast<unsigned char*>(dst + (size_t)d0 * XCP);
    auto far = [&](auto T0_, const auto& seq, const Lc& lc, int c, int lane, const uint2 (&f)[20], uint32_t kk) {
        constexpr int T0 = T0_, T1 = T0 + 6, TC = T0 > 7 ? T0 : 7, NS = sizeof(seq) / sizeof(seq[0]), PD = T0 > 7 ? CV_PDH : CV_PDF;
        uint32_t bq[28], yw[4], yz[4], P, S;
        uint4 xv, yv;
        asm("prmt.b32 %0, %1, 0, %2;" : "=r"(P) : "r"(kk), "r"(lc.sp));
        asm("prmt.b32 %0, %1, 0, %2;" : "=r"(S) : "r"(kk), "r"(lc.ss));
#pragma unroll
        for (int k = 0; 2 * k < T1 - TC + 4; k++) ldsm_x4(bq + 4 * k, lc.uc + (TC - 8) * 256 + 512 * k);
#pragma unroll
        for (int k = 0; 4 * k < T1 - TC; k++) ldsm_x4(bq + 20 + 4 * k, lc.ud + (TC - 8) * 256 + 1024 * k);
        CST(3);
        mbar_wait(cnt + 8 * c, 0);
        mbar_wait(cnt + 40, 0);
        CST(4);
        float acc[6][4] = {};
        uint32_t a[PD + 1][4];
#pragma unroll
        for (int i = -PD; i < NS + 3; i++) {
            if (i + PD < NS) ldsm_x4_t(a[(i + PD) % (PD + 1)], seq[i + PD] < 32 ? lc.a4 + (seq[i + PD] - 2) * 128 : lc.a8 + (seq[i + PD] - 34) * 256);
            if (i < 0) continue;
#pragma unroll
            for (int T = T0; T < T1; T++) {
                if (i >= NS) break;
                const int ee = seq[i] < 32 ? 2 * T - 6 - seq[i] : T + 35 - seq[i];
                if (i == 0 && T >= TC) mma_bf16(acc[T - T0], P, 0u, S, P, bq[2 * (T - TC)], bq[2 * (T - TC) + 1]);
                if (i == 1 && T >= TC) mma_bf16_k8(acc[T - T0], 0u, S, bq[20 + T - TC]);
                if (i == (T >= TC ? 2 : 0)) mma_bf16(acc[T - T0], f[19].x, 0u, f[19].y, f[19].x, bq[2 * (T - TC + 4)], bq[2 * (T - TC + 4) + 1]);
                if (seq[i] < 32 ? ee >= 0 && ee <= 9 : ee >= 10) mma_bf16(acc[T - T0], a[i % (PD + 1)][0], a[i % (PD + 1)][1], a[i % (PD + 1)][2], a[i % (PD + 1)][3], f[ee].x, f[ee].y);
            }
#pragma unroll
            for (int k = 0; k < 3; k++) {
                const int o = 256 * T0 + 512 * k;
                auto at = [&](int d) { return i - d >= 0 && i - d < NS && seq[i - d < 0 ? 0 : i - d < NS ? i - d : 0] == 2 * T0 + 4 * k - 4; };
                if (at(CV_D2)) {
                    cv_store(dq + lc.go + o, xv, yv);
                    if (layer > 19 - 2 * k) __trap();
                }
                if (at(-2)) { ldsm_x4_t(yw, lc.y + o); ldsm_x4_t(yz, lc.y + 3584 + o); }
                if (at(1)) {
#pragma unroll
                    for (int q = 0; q < 4; q++) yw[q] = add2(add2(yw[q], yz[q]), pack2(acc[2 * k + (q >> 1)][2 * (q & 1)], acc[2 * k + (q >> 1)][2 * (q & 1) + 1]));
                    stsm_x4_t(lc.y + o, yw[0], yw[1], yw[2], yw[3]);
                    xv = ldx(smem_u32(Xs) + lc.go + o);
                    __syncwarp();
                    yv = lds4(smem_u32(sm + CV_SM_Y) + c * 8192 + o + usw(lane) * 16);
                    if (layer > 20 - 2 * k) __trap();
                    if (k == 2) CST(6);
                }
            }
        }
    };
    TSTAMP1X(9, 256);
    if (threadIdx.x >= 256) {
        if (threadIdx.x < 288 && elect()) {
            mbar_init(cnt + 48, 1);
            asm volatile("fence.mbarrier_init.release.cluster;" ::: "memory");
            bulk_load(smem_u32(sm + CV_SM_T), tap + d0 * (TAPB / 16), CV_CPB * TAPB, cnt + 48);
            mbar_expect_tx(cnt + 48, CV_CPB * TAPB);
        }
        CV_IDX
        const int wgu = (warp >> 2) & 1, g = lane >> 2, ti = lane & 3;
        CST(1);
        if (warp > 8 && elect()) {
            if (warp < 15) mbar_init(cnt + 8 * (warp - 9), warp == 14 ? 8 : 4);
            else if (layer) prefetch_tmap(&tmOut);
        }
        if (warp < 13 && lane < 17 - (warp == 12)) {
            const int off = warp == 12 ? CV_SM_U : CV_SM_B + (warp == 11 ? BX_7 : (warp - 8) * BX_3), str = warp == 12 ? ULEN * 2 : BX_LEN;
#pragma unroll
            for (int c = 0; c < CV_CPB; c++) *reinterpret_cast<uint4*>(sm + off + c * str + 16 * lane) = make_uint4(0, 0, 0, 0);
        }
        fence_async_smem();
        asm volatile("bar.arrive 3, 512;" ::: "memory");
        asm volatile("bar.sync 1, 256;" ::: "memory");
        TSTAMP1X(10, 256);
        asm volatile("setmaxnreg.inc.sync.aligned.u32 168;");
        const uint32_t Tc = smem_u32(sm + CV_SM_T) + (16 + 128 * (warp & 2) + 8 * (warp & 1) + g - 2 * ti) * 4;
        uint2 fa[8][2], fn[8][2];
        auto near_taps = [&](uint2 (&f)[8][2], int c) {
#pragma unroll
            for (int m = 0; m < 16; m++) f[m >> 1][m & 1] = make_uint2(lds1v(Tc + c * TAPB + 64 * (m >> 1) - 32 * (m & 1)), lds1v(Tc + c * TAPB + 64 * (m >> 1) - 32 * (m & 1) + 512));
        };
        CST(6);
        mbar_wait(cnt + 48, 0);
        TSTAMP1X(11, 256); CST(5);
        near_taps(fa, 3 * wgu);
        near_taps(fn, 2 - wgu);
        const int hc = wgu ? warp & 3 : 4;
        const Lc lc = lane_consts(lane, hc);
        TSTAMP1X(12, 256); CST(0);
        uint32_t ya = smem_u32(sm + CV_SM_Y) + wgu * 8192 + (warp & 2) * 2048 + usw(2 * lane + (warp & 1)) * 16;
        uint64_t db = make_desc(smem_u32(Us + wgu * ULEN + UPADF), 16, 256, 3);
        if (wgu) { asm volatile("bar.sync 6, 384;" ::: "memory"); fence_async_smem(); }
        int c = wgu;
        auto chain = [&](const uint2 (&f)[8][2], auto&& meanwhile) {
            float acc[64];
            asm volatile("bar.sync %0, %1;" ::"r"(c ? 4 + wgu : 2), "r"(c ? 256 : 384) : "memory");
            TSTAMPC(1 + 3 * c);
            if (c < 2) CST(7);
            if (c == 0) fence_async_smem();
            wgmma_fence();
#pragma unroll
            for (int m = 0; m < 8; m++) {
                wgmma_rs128(acc, f[m][0], f[m][1], db - (uint64_t)(2 * m), m);
                if (m == CV_HAND && c < 4) asm volatile("bar.arrive %0, 256;" ::"r"(5 - wgu) : "memory");
            }
            wgmma_commit();
            asm volatile("griddepcontrol.launch_dependents;" ::: "memory");
            TSTAMPC(2 + 3 * c); CST(13 + (c >> 1));
            meanwhile();
            wgmma_wait<0>();
            TSTAMPC(3 + 3 * c); CST(10 + (c >> 1));
            uint32_t w[16];
#pragma unroll
            for (int j = 0; j < 16; j++) w[j] = j ? pack2(acc[4 * j] + acc[4 * j - 2], acc[4 * j + 1] + acc[4 * j - 1]) : pack2(acc[0], acc[1]);
#pragma unroll
            for (int j = 0; j < 16; j += 4) stsm_x4_t(ya + 256 * j, w[j], w[j + 1], w[j + 2], w[j + 3]);
            __syncwarp();
            if (lane == 0) mbar_arrive(cnt + 8 * c);
            c += 2; ya += 16384; db += ULEN / 4;
        };
        const uint32_t e4 = lc.e4, e8 = e4 + 428 - 4 * g;
        uint2 fl[4];
        uint32_t kk;
#pragma unroll 1
        for (;;) {
            if (c != 1) chain(fa, [&] {
                if (c == 3 || warp + c == 12) {
#pragma unroll
                    for (int k = 0; k < 19; k++) (k < 16 ? fn[(k >> 1) & 7][k & 1] : fl[k & 3]) = make_uint2(lds1(k < 10 ? e4 + 32 * k + 16 : e8 + 32 * k - 304), lds1(k < 10 ? e4 + 32 * k : e8 + 32 * k - 320));
                    fl[3] = make_uint2(lds1(lc.en), lds1(lc.en - 32));
                    kk = lds1(smem_u32(sm + CV_SM_T) + TAPB * hc + TAPE + 1672);
                }
            });
            if (c > 4) break;
            if (c == 2) { asm volatile("bar.sync 7, 384;" ::: "memory"); fence_async_smem(); }
            chain(fn, [&] { if (c == 2) near_taps(fa, 4); });
        }
        TSTAMP1X(6, 256); CST(2);
        if (wgu || warp == 8) {
            constexpr int seq[29] = {5, 6, 32, 7, 33, 8, 34, 9, 35, 10, 36, 11, 12, 13, 14, 15, 16, 17, 37, 18, 38, 19, 20, 21, 39, 22, 40, 23, 24};
            uint2 f[20];
#pragma unroll
            for (int k = 0; k < 20; k++) f[k] = k < 16 ? fn[(k >> 1) & 7][k & 1] : fl[k & 3];
            far(Int<10>(), seq, lc, hc, lane, f, kk);
        }
    } else {
        asm volatile("setmaxnreg.dec.sync.aligned.u32 88;");
        CV_IDX
        CST(5);
        const uint4* ppv = piv + tid;
        const float4* psv = sum + tid;
        const uint2* pxv = reinterpret_cast<const uint2*>(x1T + (size_t)d0 * XCP) + (tid >> 4) * 32 + (tid & 15);
        asm volatile("st.shared.u64 [%0], %1;" ::"r"(smem_u32(sm + CV_SM_O) + tid * 16), "l"((uint64_t)ppv ^ (uint64_t)psv ^ (uint64_t)pxv) : "memory");
        const int tc = (0x04302100 >> (4 * warp)) & 7;
        const Lc lc = lane_consts(lane, tc);
        pdl_sync();
        SPAN(3 + 4 * layer, 1);
        TSTAMP(0); CST(0);
        if (tid == 0) TSTAMPC(0);
        if (threadIdx.x == 0) { GSTAMP(g_tim, 15); }
        float4 sv[4];
        uint4 pv;
#pragma unroll
        for (int k = 0; k < 4; k++)
            asm volatile(CV_LD ".v4.f32 {%0,%1,%2,%3}, [%4];" : "=f"(sv[k].x), "=f"(sv[k].y), "=f"(sv[k].z), "=f"(sv[k].w) : "l"(psv + 256 * k) : "memory");
        asm volatile(CV_LD ".v4.u32 {%0,%1,%2,%3}, [%4];" : "=r"(pv.x), "=r"(pv.y), "=r"(pv.z), "=r"(pv.w) : "l"(ppv) : "memory");
        uint2 xe[CV_CPB], xo[CV_CPB];
#pragma unroll
        for (int c = 0; c < CV_NL; c++) {
            asm volatile(CV_LD ".v2.u32 {%0,%1}, [%2];" : "=r"(xe[c].x), "=r"(xe[c].y) : "l"(pxv + c * (XCP / 4)) : "memory");
            asm volatile(CV_LD ".v2.u32 {%0,%1}, [%2];" : "=r"(xo[c].x), "=r"(xo[c].y) : "l"(pxv + c * (XCP / 4) + 16) : "memory");
        }
#define CV_XD 300
#define CV_XW 0
        if (warp == CV_XW) {
            if (elect()) {
                const uint32_t c0 = clock();
                mbar_init(cnt + 56, 1);
                asm volatile("fence.mbarrier_init.release.cluster;" ::: "memory");
                mbar_expect_tx(cnt + 56, CV_CPB * 4096);
                while (clock() - c0 < CV_XD) ;
#pragma unroll
                for (int c = CV_NL; c < CV_CPB + CV_NL; c++) bulk_load(smem_u32(Xs + (c % CV_CPB) * XLEN), x1T + (size_t)(d0 + c % CV_CPB) * XCP, 4096, cnt + 56);
            }
            __syncwarp();
            CST(15);
        }
        constexpr float idm = 1.0f / DM;
        uint32_t mw[4];
        float rs[8];
#pragma unroll
        for (int k = 0; k < 4; k++) {
            const uint32_t pw = k == 0 ? pv.x : k == 1 ? pv.y : k == 2 ? pv.z : pv.w;
            mw[k] = pack2(fmaf(sv[k].x, idm, __uint_as_float(pw << 16)), fmaf(sv[k].z, idm, __uint_as_float(pw & 0xffff0000u)));
            uint32_t vr;
            asm("cvt.rn.relu.bf16x2.f32 %0, %1, %2;" : "=r"(vr) : "f"(fmaf(sv[k].z * -idm, sv[k].z, sv[k].w) * idm), "f"(fmaf(sv[k].x * -idm, sv[k].x, sv[k].y) * idm));
            const uint32_t ve = pack2(__uint_as_float(vr << 16) + 1e-5f, __uint_as_float(vr & 0xffff0000u) + 1e-5f);
            const uint32_t sd = pack2(sqrt_apx(__uint_as_float(ve << 16)), sqrt_apx(__uint_as_float(ve & 0xffff0000u)));
            rs[2 * k] = rcp_apx(__uint_as_float(sd << 16)); rs[2 * k + 1] = rcp_apx(__uint_as_float(sd & 0xffff0000u));
        }
        if (rs[0] != 123.f) TSTAMP(13);
        const uint32_t ua = smem_u32(Us) + usw(tid + UPADF / 8) * 16;
        uint32_t uw[CV_CPB][4];
#pragma unroll
        for (int c = 0; c < CV_CPB; c++) {
            if (c == CV_NL) {
                if (warp == CV_XW) { mbar_wait(cnt + 56, 0); CST(7); }
                asm volatile("bar.sync 10, 256;" ::: "memory");
            }
            if (c == 1 || c == 2) {
#pragma unroll
                for (int k = c; k < (c == 1 ? 2 : CV_CPB); k++) {
 const uint4 v = ldx(smem_u32(Xs + k * XLEN) + (tid >> 4) * 256 + (tid & 15) * 8); xe[k] = make_uint2(v.x, v.y); xo[k] = make_uint2(v.z, v.w); }
            }
            const uint32_t e0 = sub2(xe[c].x, mw[0]), e1 = sub2(xe[c].y, mw[1]), o0 = sub2(xo[c].x, mw[2]), o1 = sub2(xo[c].y, mw[3]);
            uw[c][0] = pack2(__uint_as_float(e0 << 16) * rs[0], __uint_as_float(o0 << 16) * rs[4]); uw[c][1] = pack2(__uint_as_float(e0 & 0xffff0000u) * rs[1], __uint_as_float(o0 & 0xffff0000u) * rs[5]);
            uw[c][2] = pack2(__uint_as_float(e1 << 16) * rs[2], __uint_as_float(o1 << 16) * rs[6]); uw[c][3] = pack2(__uint_as_float(e1 & 0xffff0000u) * rs[3], __uint_as_float(o1 & 0xffff0000u) * rs[7]);
            asm volatile("st.shared.v4.u32 [%0], {%1,%2,%3,%4};" ::"r"(ua + c * ULEN * 2), "r"(uw[c][0]), "r"(uw[c][1]), "r"(uw[c][2]), "r"(uw[c][3]) : "memory");
            if (c < 2) {
                asm volatile("bar.arrive %0, 384;" ::"r"(2 + 4 * c) : "memory");
                if (layer > 29 - c) __trap();
                CST(11 + c);
            }
        }
        asm volatile("bar.arrive 7, 384;" ::: "memory");
        asm volatile("bar.sync 3, 512;" ::: "memory");
        TSTAMP(1); CST(1);
        {
            auto box = [&](auto c0, auto c1, int chunk, int cb, bool full) {
                const uint32_t ea = smem_u32(Us + cb * ULEN) + usw(chunk + UPADF / 8 + (lane ? 1 : -1)) * 16, bx = smem_u32(sm + CV_SM_B + cb * BX_LEN) + chunk * 16;
                uint32_t lo[CV_CPB][4], hi[CV_CPB][2];
#pragma unroll
                for (int c = c0; c < c1; c++) {
                    lo[c][0] = 0;
#pragma unroll
                    for (int k = 1; k < 4; k++) lo[c][k] = __shfl_up_sync(~0u, uw[c][k], 1);
#pragma unroll
                    for (int k = 0; k < 2; k++) hi[c][k] = __shfl_down_sync(~0u, uw[c][k], 1);
                }
#pragma unroll
                for (int c = c0; c < c1; c++)
                    asm volatile("{\n.reg .pred p, q;\nsetp.eq.s32 p, %7, 0;\nsetp.eq.s32 q, %7, 31;\n@p ld.shared.v4.u32 {%0,%1,%2,%3}, [%6];\n@q ld.shared.v2.u32 {%4,%5}, [%6];\n}"
                                 : "+r"(lo[c][0]), "+r"(lo[c][1]), "+r"(lo[c][2]), "+r"(lo[c][3]), "+r"(hi[c][0]), "+r"(hi[c][1]) : "r"(ea + c * ULEN * 2), "r"(lane) : "memory");
#pragma unroll
                for (int c = c0; c < c1; c++) {
                    const uint32_t e[9] = {lo[c][1], lo[c][2], lo[c][3], uw[c][0], uw[c][1], uw[c][2], uw[c][3], hi[c][0], hi[c][1]};
                    uint32_t o[8], p[8], t[7], b3[5], b5[7];
#pragma unroll
                    for (int i = 0; i < 8; i++) { o[i] = __byte_perm(e[i], e[i + 1], 0x5432); p[i] = add2(e[i], o[i]); }
#pragma unroll
                    for (int i = 0; i < 5; i++) b3[i] = add2(o[i], p[i + 1]);
                    sts4(bx + c * BX_LEN + BX_3 + 160, b3);
#pragma unroll
                    for (int i = 1; i < 7; i++) { t[i] = add2(p[i], p[i + 1]); b5[i] = add2(t[i], e[i + 2]); }
                    sts4(bx + c * BX_LEN + BX_5 + 160, b5 + 2);
                    if (full) {
#pragma unroll
                        for (int i = 1; i < 5; i++) { b3[i] = add2(b3[i], t[i + 2]); t[i] = add2(t[i], b5[i + 2]); }
                        sts4(bx + c * BX_LEN + BX_7 + 272, b3 + 1);
                        sts4(bx + c * BX_LEN + BX_9 + 272, t + 1);
                    }
                }
            };
            auto reload = [&](int c, uint32_t a) { const uint4 v = lds4(a); uw[c][0] = v.x; uw[c][1] = v.y; uw[c][2] = v.z; uw[c][3] = v.w; };
            if (warp >= 6) {
#pragma unroll
                for (int c = 0; c < 3; c++) reload(c, ua - 1024 + (c + 2) * ULEN * 2);
            }
            if (warp >= 4) {
#pragma unroll
                for (int c = 3; c < 5; c++) reload(c, ua - 2048 + c * ULEN * 2);
            }
            box(Int<0>(), Int<3>(), warp < 6 ? tid : tid - 64, warp < 6 ? 0 : 2, warp < 4);
            if (warp >= 4) box(Int<3>(), Int<5>(), tid - 128, 0, true);
            else if (tid >= 128 - CV_CPB) {
                const int c = 127 - tid;
                const uint2 v = *reinterpret_cast<const uint2*>(Us + c * ULEN + UPADF);
                const float s1 = __uint_as_float(v.x << 16), s2 = s1 + __uint_as_float(v.x & 0xffff0000u), s3 = s2 + __uint_as_float(v.y << 16), s4 = s3 + __uint_as_float(v.y & 0xffff0000u);
                unsigned char* bc = sm + CV_SM_B + c * BX_LEN;
                *reinterpret_cast<uint32_t*>(bc + BX_5 + 156) = pack2(s1, s2);
                *reinterpret_cast<uint2*>(bc + BX_7 + 264) = make_uint2(v.x << 16, pack2(s2, s3));
                *reinterpret_cast<uint2*>(bc + BX_9 + 264) = make_uint2(pack2(s1, s2), pack2(s3, s4));
            }
        }
        __syncwarp();
        if (lane == 0) mbar_arrive(cnt + 40);
        TSTAMP(2); CST(2);
        if (layer && blockIdx.x == 0 && tid == 224) g_epoch = ld_epoch();
        __syncwarp();
        if ((0x6e >> warp) & 1) {
            constexpr int seq[16] = {0, 1, 2, 3, 4, 5, 6, 32, 7, 8, 9, 33, 10, 34, 11, 12};
            uint2 f[20];
            mbar_wait(cnt, 0);
            const uint32_t e8 = lc.e4 + 428 - (lane & 28);
#pragma unroll
            for (int k = 0; k < 13; k++) f[k] = make_uint2(lds1(k < 10 ? lc.e4 + 32 * k + 16 : e8 + 32 * k - 304), lds1(k < 10 ? lc.e4 + 32 * k : e8 + 32 * k - 320));
            f[19] = make_uint2(lds1(lc.en), lds1(lc.en - 32));
            far(Int<4>(), seq, lc, tc, lane, f, lds1(smem_u32(sm + CV_SM_T) + TAPB * tc + TAPE + 1672));
        }
    }
    {
        CV_IDX
        if ((0xc91 >> warp) & 1) {
            const int c = __popc(0xc91 & ((1 << warp) - 1));
            uint4 xv[2], yv[2];
#pragma unroll
            for (int k = 0; k < 2; k++) xv[k] = ldx(smem_u32(Xs + c * XLEN) + 512 * k + (lane >> 4) * 256 + (lane & 15) * 8);
            const uint32_t u0 = lds1(smem_u32(Us + c * ULEN) + (lane == 31 ? UPADF * 2 : 0));
            mbar_wait(cnt + 8 * c, 0);
#pragma unroll
            for (int k = 0; k < 2; k++) yv[k] = lds4(smem_u32(sm + CV_SM_Y) + c * 8192 + 512 * k + usw(lane) * 16);
            const uint4 yz = lds4(smem_u32(sm + CV_SM_Y) + c * 8192 + 4096 + usw(lane) * 16);
            const float kk = __uint_as_float(lds1(smem_u32(sm + CV_SM_T) + TAPB * c + TAPE + 1272) << 16);
            yv[1].x = add2(yv[1].x, yz.x); yv[1].y = add2(yv[1].y, yz.y); yv[1].z = add2(yv[1].z, yz.z);
            yv[1].w = pack2(fmaf(kk, __uint_as_float(u0 << 16), __uint_as_float(yv[1].w << 16) + __uint_as_float(yz.w << 16)),
                            fmaf(kk, __uint_as_float(u0 << 16) + __uint_as_float(u0 & 0xffff0000u), __uint_as_float(yv[1].w & 0xffff0000u) + __uint_as_float(yz.w & 0xffff0000u)));
#pragma unroll
            for (int k = 0; k < 2; k++) cv_store(dq + c * XCP * 2 + (lane >> 4) * 256 + (lane & 15) * 8 + 512 * k, xv[k], yv[k]);
        }
        TSTAMP(4); CST(8);
        if (layer == 1) {
            const int rb = (blockIdx.x >> 3) + (warp & 8) * 2, cg = blockIdx.x & 7, ch = (tid >> 3) & 31;
            const bf16* src = dst + (size_t)(cg * 80 + ch) * XCP + rb * 64 + (tid & 7) * 8;
            uint32_t v[3][4];
            __syncthreads();
            if (warp & 8) { const uint32_t c0 = clock(); while (clock() - c0 < 300) ; }
            uint32_t todo = (warp & 4) ? 3 : 7;
#pragma unroll 1
            for (int it = 0; it < SPIN_MAX; it++) {
#pragma unroll
                for (int k = 0; k < 3; k++)
                    if (todo >> k & 1)
                        asm volatile("ld.relaxed.gpu.global.v4.u32 {%0,%1,%2,%3}, [%4];" : "=r"(v[k][0]), "=r"(v[k][1]), "=r"(v[k][2]), "=r"(v[k][3]) : "l"(src + k * (32 * XCP)) : "memory");
#pragma unroll
                for (int k = 0; k < 3; k++)
                    if ((todo >> k & 1) && v[k][0] != ~0u && v[k][1] != ~0u && v[k][2] != ~0u && v[k][3] != ~0u) {
                        *reinterpret_cast<uint4*>(sm + (32 * k + ch) * 272 + ((tid & 7) + (warp & 8)) * 16) = make_uint4(v[k][0], v[k][1], v[k][2], v[k][3]);
                        todo ^= 1u << k;
                    }
                if (!todo) break;
                __nanosleep(CV_SLEEP);
            }
            __syncwarp();
            asm volatile("bar.sync %0, 256;" ::"r"(8 + (warp >> 3)) : "memory");
            uint32_t w[12];
#pragma unroll
            for (int k = 0; k < 3; k++) ldsm_x4(&w[4 * k], smem_u32(sm) + min(32 * k + lane, 79) * 272 + warp * 16);
            const uint32_t ot = smem_u32(sm + CV_SM_O) + warp * 1280, oa = ot + (lane & 7) * 160 + (lane >> 3) * 16;
            stsm_x4_t(oa, w[0], w[1], w[2], w[3]);
            stsm_x4_t(oa + 64, w[4], w[5], w[6], w[7]);
            asm volatile("stmatrix.sync.aligned.m8n8.x2.trans.shared.b16 [%0], {%1,%2};" ::"r"(oa + 128), "r"(w[8]), "r"(w[9]) : "memory");
            fence_async_smem();
            __syncwarp();
            if (lane == 0) {
                asm volatile("cp.async.bulk.tensor.3d.global.shared::cta.bulk_group [%0, {%1, %2, %3}], [%4];" ::"l"(&tmOut), "r"(cg * 80), "r"((rb >> 1) * 64 + 8 * (warp & 7)), "r"(rb & 1), "r"(ot) : "memory");
                asm volatile("cp.async.bulk.commit_group;" ::: "memory");
                asm volatile("cp.async.bulk.wait_group.read 0;" ::: "memory");
            }
        }
    }
    TSTAMP(3); CST(9); CST_END;
    GSTAMP(g_tim, 14);
    SPAN(3 + 4 * layer, 3);
}

template <int TA, int TB>
__device__ __forceinline__ void wgmma_n240(float (&d)[120], uint64_t da, uint64_t db, int acc) {
    asm volatile("{\n.reg .pred p;\nsetp.ne.b32 p, %124, 0;\nwgmma.mma_async.sync.aligned.m64n240k16.f32.bf16.bf16 {%0,%1,%2,%3,%4,%5,%6,%7,%8,%9,%10,%11,%12,%13,%14,%15,%16,%17,%18,%19,%20,%21,%22,%23,%24,%25,%26,%27,%28,%29,%30,%31,%32,%33,%34,%35,%36,%37,%38,%39,%40,%41,%42,%43,%44,%45,%46,%47,%48,%49,%50,%51,%52,%53,%54,%55,%56,%57,%58,%59,%60,%61,%62,%63,%64,%65,%66,%67,%68,%69,%70,%71,%72,%73,%74,%75,%76,%77,%78,%79,%80,%81,%82,%83,%84,%85,%86,%87,%88,%89,%90,%91,%92,%93,%94,%95,%96,%97,%98,%99,%100,%101,%102,%103,%104,%105,%106,%107,%108,%109,%110,%111,%112,%113,%114,%115,%116,%117,%118,%119}, %120, %121, p, 1, 1, %122, %123;\n}"
                 : "+f"(d[0]), "+f"(d[1]), "+f"(d[2]), "+f"(d[3]), "+f"(d[4]), "+f"(d[5]), "+f"(d[6]), "+f"(d[7]), "+f"(d[8]), "+f"(d[9]), "+f"(d[10]), "+f"(d[11]), "+f"(d[12]), "+f"(d[13]), "+f"(d[14]), "+f"(d[15]), "+f"(d[16]), "+f"(d[17]), "+f"(d[18]), "+f"(d[19]), "+f"(d[20]), "+f"(d[21]), "+f"(d[22]), "+f"(d[23]), "+f"(d[24]), "+f"(d[25]), "+f"(d[26]), "+f"(d[27]), "+f"(d[28]), "+f"(d[29]), "+f"(d[30]), "+f"(d[31]), "+f"(d[32]), "+f"(d[33]), "+f"(d[34]), "+f"(d[35]), "+f"(d[36]), "+f"(d[37]), "+f"(d[38]), "+f"(d[39]), "+f"(d[40]), "+f"(d[41]), "+f"(d[42]), "+f"(d[43]), "+f"(d[44]), "+f"(d[45]), "+f"(d[46]), "+f"(d[47]), "+f"(d[48]), "+f"(d[49]), "+f"(d[50]), "+f"(d[51]), "+f"(d[52]), "+f"(d[53]), "+f"(d[54]), "+f"(d[55]), "+f"(d[56]), "+f"(d[57]), "+f"(d[58]), "+f"(d[59]), "+f"(d[60]), "+f"(d[61]), "+f"(d[62]), "+f"(d[63]), "+f"(d[64]), "+f"(d[65]), "+f"(d[66]), "+f"(d[67]), "+f"(d[68]), "+f"(d[69]), "+f"(d[70]), "+f"(d[71]), "+f"(d[72]), "+f"(d[73]), "+f"(d[74]), "+f"(d[75]), "+f"(d[76]), "+f"(d[77]), "+f"(d[78]), "+f"(d[79]), "+f"(d[80]), "+f"(d[81]), "+f"(d[82]), "+f"(d[83]), "+f"(d[84]), "+f"(d[85]), "+f"(d[86]), "+f"(d[87]), "+f"(d[88]), "+f"(d[89]), "+f"(d[90]), "+f"(d[91]), "+f"(d[92]), "+f"(d[93]), "+f"(d[94]), "+f"(d[95]), "+f"(d[96]), "+f"(d[97]), "+f"(d[98]), "+f"(d[99]), "+f"(d[100]), "+f"(d[101]), "+f"(d[102]), "+f"(d[103]), "+f"(d[104]), "+f"(d[105]), "+f"(d[106]), "+f"(d[107]), "+f"(d[108]), "+f"(d[109]), "+f"(d[110]), "+f"(d[111]), "+f"(d[112]), "+f"(d[113]), "+f"(d[114]), "+f"(d[115]), "+f"(d[116]), "+f"(d[117]), "+f"(d[118]), "+f"(d[119])
                 : "l"(da), "l"(db), "n"(TA), "n"(TB), "r"(acc));
}

__device__ __forceinline__ void wgmma_n80(float (&d)[40], uint64_t da, uint64_t db, int acc) {
    asm volatile("{\n.reg .pred p;\nsetp.ne.b32 p, %42, 0;\nwgmma.mma_async.sync.aligned.m64n80k16.f32.bf16.bf16 {%0,%1,%2,%3,%4,%5,%6,%7,%8,%9,%10,%11,%12,%13,%14,%15,%16,%17,%18,%19,%20,%21,%22,%23,%24,%25,%26,%27,%28,%29,%30,%31,%32,%33,%34,%35,%36,%37,%38,%39}, %40, %41, p, 1, 1, 0, 1;\n}"
                 : "+f"(d[0]), "+f"(d[1]), "+f"(d[2]), "+f"(d[3]), "+f"(d[4]), "+f"(d[5]), "+f"(d[6]), "+f"(d[7]), "+f"(d[8]), "+f"(d[9]), "+f"(d[10]), "+f"(d[11]), "+f"(d[12]), "+f"(d[13]), "+f"(d[14]), "+f"(d[15]), "+f"(d[16]), "+f"(d[17]), "+f"(d[18]), "+f"(d[19]), "+f"(d[20]), "+f"(d[21]), "+f"(d[22]), "+f"(d[23]), "+f"(d[24]), "+f"(d[25]), "+f"(d[26]), "+f"(d[27]), "+f"(d[28]), "+f"(d[29]), "+f"(d[30]), "+f"(d[31]), "+f"(d[32]), "+f"(d[33]), "+f"(d[34]), "+f"(d[35]), "+f"(d[36]), "+f"(d[37]), "+f"(d[38]), "+f"(d[39])
                 : "l"(da), "l"(db), "r"(acc));
}

constexpr int A1_THREADS = 384;
constexpr int A1_NST = 4;
#define A1_SKEW 8
constexpr int A1_STAGE = 16384 + WQ_STAGE;
constexpr int A1_KVP = 336;
constexpr int A1_SM_KV = 2 * A1_STAGE;
constexpr int A1_SM_END = A1_NST * A1_STAGE;
constexpr int A1_SM_BAR = A1_SM_END + 3072 + 3 * WOB + 64;
constexpr int A1_SM_RS = A1_SM_END + 512;
constexpr int A1_SM_W0 = A1_SM_END + 3072, A1_SM_W3 = A1_SM_END - 3 * WOB, A1_SM_A1 = 2 * WOB, A1_SM_A0 = A1_SM_A1 + 61440;
constexpr int A1_SM_XA = A1_SM_W0 + 2 * WOB, A1_SM_XB = A1_SM_XA + 2048;
constexpr int A1_SMEM = A1_SM_BAR + 512 + 7 * CST_EXTRA / 4;
static_assert(A1_SM_W3 >= A1_SM_KV + 144 * A1_KVP && A1_SM_W3 % 512 == 0 && A1_SM_A1 % 1024 == 0 && A1_SM_A0 <= A1_SM_KV && A1_SM_A0 + 61440 <= A1_SM_W3 && A1_SMEM <= 232448 && 11 * 4096 <= A1_STAGE, "layout");
__device__ __forceinline__ constexpr uint32_t wo_off(int h) { return h * WOB + (h < 3 ? A1_SM_W0 : h < 6 ? A1_SM_W3 - 3 * WOB : -6 * WOB); }
#define A1_FRED "red.relaxed.gpu.global.add.u32"
#define A1_FLD "ld.acquire.gpu.global.u32"
#define ST_SLEEP 20
#define ST_SLEEP0 300
#define WO_LATE bar_done
#define A1_P0 2
#define A1_PW (kb - 2)
#define A1_FSPIN SPIN_MAX
#define A1_FSLEEP 40
#define YT_LAYER 1
#define WOT 352
#define A1_WOAT 6

template <int L>
__device__ __forceinline__ void a1_mainloop(float (&acc)[120], uint32_t sbase, uint32_t bars, int wg, int tile) {
    constexpr int layer = L; (void)layer;
    const uint64_t da0 = L ? make_desc(sbase + wg * 8192, 8192, 1024, 1) : make_desc(sbase + wg * 8192, 16, 1024, 1), db0 = make_desc(sbase + 16384, 1024, 256, 3);
#pragma unroll 1
    for (int t = 0;; t++) {
        const int st = t % A1_NST;
        mbar_wait(bars + 8 * st, (t / A1_NST) & 1);
        if (t == A1_SKEW && wg == 0) mbar_wait(bars + 160, 0);
        TSTAMP3(1 + t);
        if (t == 0) CSA(0);
        wgmma_fence();
#pragma unroll
        for (int kk = 0; kk < 4; kk++) wgmma_n240<L, 1>(acc, da0 + (uint32_t)(st * (A1_STAGE / 16) + kk * (L ? 128 : 2)), db0 + (uint32_t)(st * (A1_STAGE / 16) + (kk >> 1) * (WQ_STAGE / 32) + (kk & 1) * 32), kk ? 1 : t);
        wgmma_commit();
        if (t == 9) break;
        if (t == A1_SKEW - 1 && wg == 0) wgmma_wait<0>(); else wgmma_wait<1>();
        if (t > 0 && (threadIdx.x & 127) == 0) {
            if (t != A1_SKEW || wg) mbar_arrive(bars + 8 * (A1_NST + (t - 1) % A1_NST));
            if (t == A1_SKEW - 1 && wg == 0) mbar_arrive(bars + 8 * (A1_NST + t % A1_NST));
        }
    }
}

template <bool MAP>
__global__ void __launch_bounds__(A1_THREADS, 1) a1_kernel(const __grid_constant__ Par in, const __grid_constant__ CUtensorMap tmX, const __grid_constant__ CUtensorMap tmR,
                                                           const __grid_constant__ CUtensorMap tmX1, const __grid_constant__ KgMaps tmW, const __grid_constant__ TileTab tab) {
#define layer in.layer
    const unsigned char* const wo = reinterpret_cast<const unsigned char*>(in.wop);
    float2* const rsum = reinterpret_cast<float2*>(in.sum);
    uint4* const of = in.of;
    extern __shared__ __align__(1024) unsigned char stg[];
    const uint32_t sbase = smem_u32(stg);
    const uint32_t bars = sbase + A1_SM_BAR;
    const uint32_t bar_stat = bars + 64, bar_kv = bars + 72, bar_rd = bars + 168;
    const uint32_t bar_wo = bars + 208, bar_done = bars + 216, bar_pv = bars + 224, bar_kvf = bars + 232, bar_f2 = bars + 248, bar_e2 = bars + 384, que = bars + 448;
    const int tid = threadIdx.x;
    CSK(0);
    const int w = __shfl_sync(~0u, tid >> 5, 0), wg = w >> 2;
    uint32_t smid;
    asm volatile("mov.u32 %0, %smid;" : "=r"(smid));
    const uint4 tv = tab.e[(MAP ? smid : blockIdx.x) + (tid & (smid >> 12))];
    const uint64_t pa = reinterpret_cast<const uint64_t*>(&in)[tid & (smid >> 12)], pb = reinterpret_cast<const uint64_t*>(&in)[6 + (tid & (smid >> 12))];
    const bool one = elect();
    uint32_t tz;
    const unsigned char* wq;
    auto entry = [&] { tz = __shfl_sync(~0u, tv.z, 0); wq = (const unsigned char*)(((uint64_t)__shfl_sync(~0u, tv.y, 0) << 32) | __shfl_sync(~0u, tv.x, 0)); };
    auto issue_w = [&](unsigned it) { bulk_load(sbase + (it % A1_NST) * A1_STAGE + 16384, wq + it * WQ_STAGE, WQ_STAGE, bars + 8 * (it % A1_NST)); };
    auto issue_x = [&](unsigned it, int kb) {
        asm volatile("cp.async.bulk.tensor.5d.shared::cluster.global.mbarrier::complete_tx::bytes [%0], [%1, {%3, %3, %3, %4, %5}], [%2];"
                     ::"r"(sbase + (it % A1_NST) * A1_STAGE), "l"(&tmX), "r"(bars + 8 * (it % A1_NST)), "r"(0), "r"(tz & 15), "r"(kb) : "memory");
    };
    auto first_x = [&] {
        issue_x(0, (tz >> 16) & 7); issue_x(1, ((tz >> 16) & 7) + 1);
    };
    auto expect = [&] {
#pragma unroll
        for (int i = 0; i < A1_NST; i++) mbar_expect_tx(bars + 8 * i, A1_STAGE);
    };
    if (w == 8) {
        if (one) {
            prefetch_tmap(&tmX); prefetch_tmap(&tmW.q);
#pragma unroll
            for (int i = 0; i < A1_NST; i++) mbar_init(bars + 8 * i, 1);
            asm volatile("fence.mbarrier_init.release.cluster;" ::: "memory");
        }
        __syncwarp();
        asm volatile("bar.arrive 0, 384;" ::: "memory");
        if (smid >> 12) __trap();
        entry();
        if ((tz & 0x80000010u) == 16) {
            if (one) {
                issue_w(0);
                asm volatile("griddepcontrol.wait;" ::: "memory");
                first_x();
                issue_w(1);
                expect();
                asm volatile("griddepcontrol.launch_dependents;" ::: "memory");
            }
#pragma unroll
            for (int kb = 2; kb < A1_NST; kb++) {
                __syncwarp();
                mbar_wait(bars + 8 * (kb - 2), 0);
                if (one) { issue_x(kb, ((tz >> 16) & 7) + kb); issue_w(kb); }
                CSK(6 + kb);
            }
        }
        __syncwarp();
        if (!(tz & 16) && blockIdx.x < 128) kgen_first(in, tmW, sbase + A1_SM_W0, bars - 24, one);
        __syncwarp();
    }
    if (w > 8) CSK(8);
    const bool gen = w != 8 && in.logA && blockIdx.x < 128;
    KgPar kp;
    const int w11 = w < 8 ? 2 * (w & 3) + (w >> 2) : w - 1;
    if (gen) kgen_load(in, reinterpret_cast<const bf16*>(pa), w11, kp);
    if (w > 8) CSK(9);
    if (w == 8) {
        const int tile = tz >> 24, mb = tz & 15, hg = (tz >> 8) & 7, kb0 = (tz >> 16) & 7;
        const unsigned l1 = (tz >> 4) & 1;
        if (__builtin_expect(!l1, 0)) {
            CSK(1);
            const uint32_t ep = ld_epoch();
            if (one) {
                kgen_side(in, sbase + A1_SM_W0, bars - 24);
                if (tile < 128) { first_x(); expect(); }
                asm volatile("cp.async.bulk.wait_group 0;" ::: "memory");
            }
            __syncwarp();
            asm volatile("bar.arrive 10, 96;" ::: "memory");
            CSK(6);
            if (tile < 128) {
                await_all(96 + 32 * hg, ep * 15);
                if (one) issue_w(0);
                __syncwarp();
                mbar_wait(bars, 0);
                if (one) { issue_w(1); issue_x(2, kb0 + 2); issue_w(2); }
            }
            CSK(7);
            asm volatile("bar.sync 3, 384;" ::: "memory");
            if (tile < 128 && one) {
                fence_async_smem();
                issue_x(3, kb0 + 3); issue_w(3);
                mbar_expect_tx(bars + 240, 20480);
                bulk_load(sbase + A1_SM_W0, in.x + (size_t)(mb * 128 + hg * 16) * DM, 20480, bars + 240);
            }
            __syncwarp();
            CSK(9);
        } else asm volatile("bar.sync 3, 64;" ::: "memory");
        if (tile < 128 && elect()) {
#pragma unroll 1
            for (unsigned kb = A1_NST; kb < 10; kb++) {
                mbar_wait(bars + 8 * (A1_NST + kb % A1_NST), ((kb / A1_NST) - 1) & 1);
                if (l1 && kb < 9) mbar_wait(bar_rd + 8 * (kb - A1_NST), 0);
                mbar_expect_tx(bars + 8 * (kb % A1_NST), A1_STAGE);
                issue_x(kb, kb < 5 ? kb + kb0 : kb - kb0); issue_w(kb);
                if (kb == (l1 ? A1_WOAT : 9)) {
                    if (!l1) { mbar_wait(bar_stat, 0); asm volatile("fence.proxy.async.global;" ::: "memory"); }
                    mbar_expect_tx(bar_wo, 8 * WOB);
                    bulk_load(sbase + A1_SM_W0, wo + hg * 8 * WOB, 2 * WOB, bar_wo);
                }
            }
            mbar_wait(bars + 8 * (A1_NST + 3), 1);
            bulk_load(sbase + A1_SM_W3, wo + (hg * 8 + 3) * WOB, 3 * WOB, bar_wo);
        }
        CSA(4); CSA_END;
        return;
    }
    {
        if (w < 8 && one) {
#pragma unroll 1
            for (uint32_t c = (w & 4 ? w & 2 ? 0x1111112'01111111ull : 0x1111111'01111184ull : w & 2 ? 0x3122222'01111111ull : 0x1111132'02220000ull) >> (32 * (w & 1)), b = bars + 56 * w; c; c >>= 4, b += 8)
                if (c & 15) mbar_init(b, c & 15);
            asm volatile("fence.mbarrier_init.release.cluster;" ::: "memory");
        }
        __syncwarp();
        asm volatile("bar.sync 0, 384;" ::: "memory");
        if (layer) {
            if (w == 9) asm volatile("bar.arrive 3, 64;" ::: "memory");
        } else {
            if (gen) { SPAN(0, 0); SPAN(0, 1); kgen_tables(in, reinterpret_cast<uint4*>(stg + 3 * A1_STAGE), w11, kp); }
            else if (w != 11 && w11 > 1) asm volatile("bar.arrive 9, 352;" ::: "memory");
            __syncwarp();
            if (w11 < 2) {
                asm volatile("bar.sync 10, 96;" ::: "memory");
                kgen_sums(in, sbase + A1_SM_W0, w11);
                __syncwarp();
                asm volatile("bar.arrive 9, 352;" ::: "memory");
                CSK(1);
            }
            if (w == 9) asm volatile("bar.sync 3, 384;" ::: "memory"); else asm volatile("bar.arrive 3, 384;" ::: "memory");
        }
    }
    tz = __shfl_sync(~0u, tv.z + (uint32_t)(pb >> 32), 0);
    const int tile = tz >> 24, mb = tz & 15, hg = (tz >> 8) & 7;
    float2* rst = reinterpret_cast<float2*>(stg + A1_SM_RS) + 8;
    if (wg == 2) {
        if (w == 11 && layer == 0) {
            asm volatile("bar.sync 9, 352;" ::: "memory");
            CSK(5);
            if (one) publish(64);
            __syncwarp();
            CSK(6);
        }
        if (tile >= 128) { sm_idle(layer); return; }
        if (w == 10) {
            if (one) { prefetch_tmap(&tmR); prefetch_tmap(&tmX1); }
            uint32_t ns;
            asm volatile("mov.u32 %0, %nsmid;" : "=r"(ns));
            if (MAP && ns != 132) __trap();
        }
        __syncwarp();
        if (w == 9) {
            if (layer && one) {
                mbar_expect_tx(bar_stat, 3840);
                bulk_load(sbase + A1_SM_XB, g_xb + tile * 240, 3840, bar_stat);
            }
            __syncwarp();
            uint4* pre = of + (mb * 8 + hg) * 1280 + (tid - 288);
#pragma unroll 1
            for (int k = 0; k < 5 + 5 * layer; k++) {
#pragma unroll
                for (int i = 0; i < 8; i++) asm volatile("st.global.v4.u32 [%0], {%1,%1,%1,%1};" ::"l"(pre + 32 * i), "r"(~0u) : "memory");
                pre += k < 5 ? 256 : XCP / 8;
                if (k == 4) {
                    CSA(2);
                    asm volatile("fence.acq_rel.gpu;" ::: "memory");
                    asm volatile("fence.proxy.async.global;" ::: "memory");
                    __syncwarp();
                    if (tid == 288) mbar_arrive(bar_done);
                    CSA(3);
                    pre = reinterpret_cast<uint4*>(g_yT) + tile * (5 * XCP / 8) + (tid - 288);
                }
            }
            if (layer == 0) {
                asm volatile("griddepcontrol.launch_dependents;" ::: "memory");
                await_all(64, ld_epoch() * gridDim.x);
                CSA(5);
                float4 a[2] = {};
#pragma unroll
                for (int k = 0; k < 10; k++)
#pragma unroll
                    for (int h = 0; h < 2; h++) {
                        const int c4 = min(tid - 288 + 32 * h, 59);
                        const float4 v = __ldcg(reinterpret_cast<const float4*>(g_csp + (k / 5) * 9600 + (k % 5) * 640 + hg * 80) + c4 + (c4 / 20) * 780);
                        a[h].x += v.x; a[h].y += v.y; a[h].z += v.z; a[h].w += v.w;
                    }
#pragma unroll
                for (int h = 0; h < 2; h++)
#pragma unroll
                    for (int k = 0; k < 4; k++) {
                        const float c = 0.5f * (k == 0 ? a[h].x : k == 1 ? a[h].y : k == 2 ? a[h].z : a[h].w), c1 = c - rbf(c), c2 = c1 - rbf(c1);
                        *reinterpret_cast<uint4*>(stg + A1_SM_XB + (4 * min(tid - 288 + 32 * h, 59) + k) * 16) = make_uint4(pack2(c, c1), pack2(c2, 0.f), 0u, 0u);
                    }
                fence_async_smem();
                __syncwarp();
                if (one) {
                    bulk_store(g_xb + tile * 240, sbase + A1_SM_XB, 3840);
                    asm volatile("cp.async.bulk.commit_group;" ::: "memory");
                    asm volatile("cp.async.bulk.wait_group.read 0;" ::: "memory");
                    mbar_arrive(bar_stat);
                }
                __syncwarp();
                CSA(1);
            }
            TSTAMP1T(9, 288);
        } else {
            const int j = tid - 320;
            const uint32_t tag = ld_epoch();
            if (tid == 352) sm_started(layer);
            const int ch = j & 7, kg = (j >> 3) & 3;
            const unsigned char* src = stg + (layer ? (j >> 5) * 8192 + (hg & 3) * 2048 : A1_SM_W0 + (j >> 2) * 1280);
            const int of0 = layer ? kg * 128 + ((ch ^ kg) << 4) : (j & 7) << 4, ofx = layer ? 576 : 64, ofy = layer ? 1024 : 128;
            float s[8], q[8], p0[8];
#pragma unroll
            for (int i = 0; i < 8; i++) { s[i] = 0.f; q[i] = 0.f; }
#pragma unroll 1
            for (int it = 0; it < 5; it++) {
                uint4 v[4];
                mbar_wait(layer ? bars + 8 * (it % A1_NST) : bars + 240, layer * it / A1_NST);
#pragma unroll
                for (int k = 0; k < 4; k++) v[k] = *reinterpret_cast<const uint4*>(src + (layer ? (it % A1_NST) * A1_STAGE : it * 256) + (k & 1 ? of0 ^ ofx : of0) + (k >> 1) * ofy);
                if (it == 0) {
                    const uint4 pv = *reinterpret_cast<const uint4*>(src + (layer ? ch << 4 : 0));
                    const uint32_t w[4] = {pv.x, pv.y, pv.z, pv.w};
#pragma unroll
                    for (int i = 0; i < 4; i++) { p0[2 * i] = __uint_as_float((layer ? w[i] : w[0]) << 16); p0[2 * i + 1] = __uint_as_float(layer ? w[i] & 0xffff0000u : w[0] << 16); }
                }
                asm volatile("" :: "r"(v[0].x), "r"(v[1].x), "r"(v[2].x), "r"(v[3].x), "f"(p0[0]) : "memory");
                __syncwarp();
                if ((tid & 31) == 0) mbar_arrive(bar_rd + 8 * it);
#pragma unroll
                for (int k = 0; k < 4; k++) {
                    const uint32_t w[4] = {v[k].x, v[k].y, v[k].z, v[k].w};
#pragma unroll
                    for (int i = 0; i < 4; i++) {
                        const float a = __uint_as_float(w[i] << 16) - p0[2 * i], b = __uint_as_float(w[i] & 0xffff0000u) - p0[2 * i + 1];
                        s[2 * i] += a; s[2 * i + 1] += b; q[2 * i] = fmaf(a, a, q[2 * i]); q[2 * i + 1] = fmaf(b, b, q[2 * i + 1]);
                    }
                }
            }
            float o[4];
            int row;
            if (layer == 0) {
                float s0 = ((s[0] + s[1]) + (s[2] + s[3])) + ((s[4] + s[5]) + (s[6] + s[7])), q0 = ((q[0] + q[1]) + (q[2] + q[3])) + ((q[4] + q[5]) + (q[6] + q[7]));
#pragma unroll
                for (int o = 1; o <= 2; o <<= 1) { s0 += __shfl_xor_sync(~0u, s0, o); q0 += __shfl_xor_sync(~0u, q0, o); }
                if ((j & 3) == 0) {
                    const float d = s0 * (1.0f / DM);
                    const uint32_t ms = pack2(p0[0] + d, sqrt_apx(rbf(rbf(fmaxf(fmaf(-d, d, q0 * (1.0f / DM)), 0.f)) + 1e-5f)));
                    asm volatile("st.global.cg.u64 [%0], %1;" ::"l"(g_rstat + mb * 128 + (j & 4) * 16 + hg * 8 + (j >> 3)), "l"(tagw(ms, tag)) : "memory");
                    g_piv[mb * 128 + hg * 16 + ((j >> 2) & 8) + (j & 4) + ((j >> 3) & 3)] = __ushort_as_bfloat16((unsigned short)ms);
                }
                ulonglong2 v;
#pragma unroll 1
                for (int it = 0; it < SPIN_MAX; it++) {
                    v = ld_tag2(reinterpret_cast<const ulonglong2*>(g_rstat + mb * 128) + j);
                    if (__all_sync(~0u, tag_ok(v, tag))) break;
                    __nanosleep(100);
                }
                o[0] = __uint_as_float((uint32_t)v.x << 16); o[1] = rcp_apx(__uint_as_float((uint32_t)v.x & 0xffff0000u));
                o[2] = __uint_as_float((uint32_t)v.y << 16); o[3] = rcp_apx(__uint_as_float((uint32_t)v.y & 0xffff0000u));
                row = 2 * j;
            } else {
#pragma unroll
                for (int i = 0; i < 4; i++) {
                    const bool up = kg & 2;
                    const float ss = __shfl_xor_sync(~0u, up ? s[i] : s[i + 4], 16), qq = __shfl_xor_sync(~0u, up ? q[i] : q[i + 4], 16);
                    s[i] = (up ? s[i + 4] : s[i]) + ss; q[i] = (up ? q[i + 4] : q[i]) + qq; p0[i] = up ? p0[i + 4] : p0[i];
                }
#pragma unroll
                for (int i = 0; i < 2; i++) {
                    const bool up = kg & 1;
                    const float ss = __shfl_xor_sync(~0u, up ? s[i] : s[i + 2], 8), qq = __shfl_xor_sync(~0u, up ? q[i] : q[i + 2], 8);
                    s[i] = (up ? s[i + 2] : s[i]) + ss; q[i] = (up ? q[i + 2] : q[i]) + qq; p0[i] = up ? p0[i + 2] : p0[i];
                }
                uint4* gp = g_halo + 86016 + mb * 512 + j;
                const float d0 = s[0] * (1.0f / 80.0f), d1 = s[1] * (1.0f / 80.0f);
                asm volatile("st.relaxed.gpu.global.v4.f32 [%0], {%1,%2,%3,%4};" ::"l"(gp + hg * 64), "f"(p0[0] + d0), "f"(fmaxf(fmaf(-d0, s[0], q[0]), 0.f)), "f"(p0[1] + d1), "f"(fmaxf(fmaf(-d1, s[1], q[1]), 0.f)) : "memory");
                __nanosleep(ST_SLEEP0);
                uint32_t pw[8][4], todo = 0xff;
#pragma unroll 1
                for (int it = 0; it < SPIN_MAX; it++) {
#pragma unroll
                    for (int k = 0; k < 8; k++)
                        if (todo >> k & 1) asm volatile("ld.relaxed.gpu.global.v4.u32 {%0,%1,%2,%3}, [%4];" : "=r"(pw[k][0]), "=r"(pw[k][1]), "=r"(pw[k][2]), "=r"(pw[k][3]) : "l"(gp + k * 64) : "memory");
#pragma unroll
                    for (int k = 0; k < 8; k++)
                        if (__all_sync(~0u, pw[k][0] != ~0u && pw[k][1] != ~0u && pw[k][2] != ~0u && pw[k][3] != ~0u)) todo &= ~(1u << k);
                    if (!todo) break;
                    __nanosleep(ST_SLEEP);
                }
#pragma unroll
                for (int r = 0; r < 2; r++) {
                    float mean = 0.f, m2 = 0.f;
#pragma unroll
                    for (int k = 0; k < 8; k++) mean += __uint_as_float(pw[k][2 * r]);
                    mean *= 0.125f;
#pragma unroll
                    for (int k = 0; k < 8; k++) {
                        const float dm = __uint_as_float(pw[k][2 * r]) - mean;
                        m2 += fmaf(80.0f * dm, dm, __uint_as_float(pw[k][2 * r + 1]));
                    }
                    o[2 * r] = rbf(mean);
                    o[2 * r + 1] = rcp_apx(rbf(sqrt_apx(rbf(rbf(m2 * (1.0f / DM)) + 1e-5f))));
                }
                row = (j >> 5) * 64 + (j & 7) * 8 + ((j >> 3) & 3) * 2;
                if (hg == 0) *reinterpret_cast<uint32_t*>(g_piv + SEQ + mb * 128 + 2 * (row & 60) + 4 * (row >> 6) + (row & 3)) = __byte_perm(__float_as_uint(o[0]), __float_as_uint(o[2]), 0x7632);
            }
#pragma unroll
            for (int r = 0; r < 2; r++)
                *reinterpret_cast<uint4*>(stg + A1_SM_XA + (row + r) * 16) = make_uint4(__byte_perm(__float_as_uint(-o[2 * r]), 0, 0x3232), __float_as_uint(-o[2 * r]) >> 16, 0u, 0u);
            *reinterpret_cast<float4*>(rst + row + (row >> 6) * 8) = make_float4(o[0], o[1], o[2], o[3]);
            fence_async_smem();
            TSTAMP1T(7, 320); CSA(1);
            if (tid == 320) DBGC(44);
            __syncwarp();
            if ((tid & 31) == 0) mbar_arrive(bar_stat);
        }
        CSA(4); CSA_END;
        if (tid == 320) DBGCAL(0);
        if (tid == WOT) {
            mbar_wait(WO_LATE, 0);
            mbar_wait(bar_done, 0);
            bulk_load(sbase, wo + (hg * 8 + 6) * WOB, 2 * WOB, bar_wo);
            bulk_load(sbase + A1_SM_W0 + 2 * WOB, wo + (hg * 8 + 2) * WOB, WOB, bar_wo);
        }
        __syncwarp();
#define FWA 11
#define FWB 10
        if (w == FWA || w == FWB) {
            const int cw = w == FWB;
            const uint32_t* fl = reinterpret_cast<const uint32_t*>(rsum + 2 * SEQ) + (((layer * 16 + mb) * 2 + cw) * 8 + (tid & 7)) * FSTR;
            const unsigned char* src = reinterpret_cast<const unsigned char*>(of) + mb * 163840 + cw * 10240 + (tid & 7) * 20480;
            const uint32_t sl = sbase + (cw ? A1_SM_A1 : A1_SM_A0);
            mbar_wait(cw ? bar_done : bar_kvf, 0);
            if ((tid & 31) == 0) {
                mbar_expect_tx(bar_f2 + 64 * cw + 64, 10240);
                tma_load_3d(sl + 51200, &tmR, layer ? 0 : hg * 80, layer ? hg * 80 : mb * 64, layer ? mb * 2 + cw : cw, bar_f2 + 64 * cw + 64);
            }
            __syncwarp();
            uint32_t pend = 0xffu & ~(1u << hg), v = 0;
            const uint32_t bo = wo_off((tid & 7) + ((tid & 7) < hg)) >> 4, lt = (1u << (tid & 31)) - 1;
#pragma unroll 1
            for (int it = 0; pend && it < 2 * SPIN_MAX; it++) {
                if (v != 4 && (pend >> (tid & 31) & 1)) asm volatile(A1_FLD " %0, [%1];" : "=r"(v) : "l"(fl) : "memory");
                uint32_t fr;
                asm volatile("{\n.reg .pred p;\nmbarrier.test_wait.parity.shared::cta.b64 p, [%1], 0;\nselp.b32 %0, 1, 0, p;\n}" : "=r"(fr) : "r"(bar_e2 + 16 * cw + (tid & 1) * 8) : "memory");
                fr = __ballot_sync(~0u, fr);
                uint32_t m = __ballot_sync(~0u, v == 4 || it >= A1_FSPIN) & pend;
                const int q = 8 - __popc(pend) + __popc(m & lt);
                m &= __ballot_sync(~0u, q < ((fr & 2) ? 8 : (fr & 1) ? 7 : 5));
                pend ^= m;
                if (m >> (tid & 31) & 1) DBGC(12 + cw * 8 + (tid & 7));
                if (!m) __nanosleep(A1_FSLEEP);
                else asm volatile("fence.proxy.async.global;" ::: "memory");
                if (m >> (tid & 31) & 1) {
                    bulk_load(q == 7 && !cw ? sbase + A1_SM_W0 : sl + (q < 6 ? q : q - 6) * 10240, src, 10240, bar_f2 + 64 * cw + 8 * q);
                    asm volatile("st.shared.u32 [%0], %1;" ::"r"(que + 32 * cw + 4 * q), "r"(bo) : "memory");
                    mbar_expect_tx(bar_f2 + 64 * cw + 8 * q, 10240);
                    DBGC(44 + cw * 8 + q);
                }
                __syncwarp();
            }
        }
    } else if (tile < 128) {
        SPAN(1 + 4 * layer, 0);
        constexpr int on = 1;
        float acc[120];
        const int lane = tid & 31, warp = w & 7, g = lane >> 2, t = lane & 3;
        if (on) {
            SPAN(1 + 4 * layer, 1);
            TSTAMP1(0);
            if (threadIdx.x == 0) { GSTAMP(g_tim1, 15); }
            TSTAMP3(0);
            if (tid == 0) TSTAMP2(0);
            TSTAMP4(0);
            if (tid == 0) DBGC(60);
            if (layer == 0) a1_mainloop<0>(acc, sbase, bars, wg, tile); else a1_mainloop<1>(acc, sbase, bars, wg, tile);
            uint32_t ok;
            asm volatile("{\n.reg .pred p;\nmbarrier.test_wait.parity.shared::cta.b64 p, [%1], 0;\nselp.b32 %0, 1, 0, p;\n}" : "=r"(ok) : "r"(bar_stat) : "memory");
            if (tid == 128 && !ok) mbar_arrive(bars + 160);
            __syncwarp();
            mbar_wait(bar_stat, 0);
            wgmma_fence();
            wgmma_n240<0, 0>(acc, make_desc(sbase + A1_SM_XA + wg * 1024, 0, 128, 0), make_desc(sbase + A1_SM_XB, 0, 128, 0), 1);
            wgmma_commit();
            if (tid == 128 && ok) mbar_arrive(bars + 160);
            mbar_wait(bars + 8 * (A1_NST + 3), 1);
        }
        const float2* rw = rst + 16 * warp + 8 * wg;
        const float rb0 = rw[g + 8].y, ra = rw[g].y * 0.22360679774997896f, rb = rb0 * 0.22360679774997896f;
        wgmma_wait<0>();
        if ((tid & 127) == 0) mbar_arrive(bar_done);
        TSTAMP1(2); CSA(1);
        TSTAMP1T(13, 224);
        if ((tid & 127) == 0) DBGC(62 - wg);
        uint32_t f[2][30];
#pragma unroll
        for (int j = 10; j < 30; j++) f[1][j] = pack2(acc[4 * j + 2], acc[4 * j + 3]);
        if ((warp & 3) == 3) {
            uint4* hout = g_halo + (((layer * 16 + mb) * 8 + hg) * 2 + wg) * 168;
#pragma unroll
            for (int j = 0; j < 20; j += 4)
                asm volatile("st.relaxed.gpu.global.v4.u32 [%0], {%1,%2,%3,%4};" ::"l"(hout + 8 * j + lane), "r"(f[1][10 + j]), "r"(f[1][11 + j]), "r"(f[1][12 + j]), "r"(f[1][13 + j]) : "memory");
            if (t == 0) asm volatile("st.relaxed.gpu.global.f32 [%0], %1;" ::"l"(reinterpret_cast<float*>(hout + 160) + g), "f"(rb0) : "memory");
        }
        TSTAMP1T(12, 224);
        const uint32_t kvw = sbase + A1_SM_KV + (16 * warp + 8 * wg) * A1_KVP;
        const uint32_t mrow = kvw + (lane & 7) * A1_KVP + (lane >> 3) * 16;
#pragma unroll
        for (int j = 0; j < 20; j += 4) stsm_x4(mrow + 16 * A1_KVP + 16 * j, f[1][10 + j], f[1][11 + j], f[1][12 + j], f[1][13 + j]);
        __syncwarp();
        if (lane == 0 && (warp & 3) != 3) mbar_arrive(bar_kv + 8 * (warp + 1));
#pragma unroll
        for (int j = 0; j < 30; j++) f[0][j] = pack2(acc[4 * j], acc[4 * j + 1]);
        stsm_x4(mrow + 8 * A1_KVP + 160, f[0][20], f[0][21], f[0][22], f[0][23]);
        stsm_x4(mrow + 8 * A1_KVP + 224, f[0][24], f[0][25], f[0][26], f[0][27]);
        asm volatile("stmatrix.sync.aligned.m8n8.x2.shared.b16 [%0], {%1,%2};" ::"r"(mrow + 8 * A1_KVP + 288), "r"(f[0][28]), "r"(f[0][29]) : "memory");
#pragma unroll
        for (int j = 0; j < 10; j++) f[1][j] = pack2(acc[4 * j + 2], acc[4 * j + 3]);
        __syncwarp();
        uint32_t vb[10][2], vp[12], kp[12];
#pragma unroll
        for (int j = 0; j < 10; j += 2) ldsm_x4_t(&vb[j][0], kvw + (8 + (lane & 15)) * A1_KVP + 160 + (lane >> 4) * 16 + 16 * j);
        const bool up0 = 2 * t > g, up1 = 2 * t + 1 > g, edge = (mb | (warp & 3)) == 0;
        float rk[4];
        auto above = [&]() {
            mbar_wait(bar_kv + 8 * warp, 0);
#pragma unroll
            for (int j = 0; j < 12; j += 4) ldsm_x4(&kp[j], mrow + 16 * j);
            rk[0] = rw[2 * t - (up0 ? 8 : 0)].y; rk[1] = rw[2 * t + 1 - (up1 ? 8 : 0)].y;
#pragma unroll
            for (int j = 0; j < 12; j += 4) ldsm_x4_t(&vp[j], mrow + 160 + 16 * j - (j == 8 ? (lane & 16) * 2 : 0));
            __syncwarp();
            if (lane == 0) mbar_arrive(bar_kvf);
        };
        auto halo = [&]() {
            if (lane == 0) mbar_arrive(bar_kvf);
            const uint4* hin = g_halo + (((layer * 16 + mb - 1) * 8 + hg) * 2 + wg) * 168;
            uint32_t hv[22] = {};
            rk[0] = rw[2 * t].y; rk[1] = rw[2 * t + 1].y;
            if (mb > 0) {
#pragma unroll 1
                for (int it = 0; it < SPIN_MAX; it++) {
#pragma unroll
                    for (int k = 0; k < 20; k += 4)
                        asm volatile("ld.relaxed.gpu.global.v4.u32 {%0,%1,%2,%3}, [%4];" : "=r"(hv[k]), "=r"(hv[k + 1]), "=r"(hv[k + 2]), "=r"(hv[k + 3]) : "l"(hin + 8 * k + lane) : "memory");
                    asm volatile("ld.relaxed.gpu.global.v2.u32 {%0,%1}, [%2];" : "=r"(hv[20]), "=r"(hv[21]) : "l"(reinterpret_cast<const uint2*>(hin + 160) + t) : "memory");
                    uint32_t m = max(hv[20], hv[21]);
#pragma unroll
                    for (int k = 0; k < 20; k += 2) m = __vimax3_u32(m, hv[k], hv[k + 1]);
                    if (!__any_sync(~0u, m == ~0u)) break;
                }
            }
            if (lane == 0) DBGC(52 - 16 * wg);
#pragma unroll
            for (int j = 0; j < 10; j++) {
                kp[j] = hv[j];
                asm volatile("movmatrix.sync.aligned.m8n8.trans.b16 %0, %1;" : "=r"(vp[j]) : "r"(hv[10 + j]));
            }
            if (up0) rk[0] = __uint_as_float(hv[20]);
            if (up1) rk[1] = __uint_as_float(hv[21]);
        };
        rk[2] = rw[2 * t + (up0 ? 0 : 8)].y; rk[3] = rw[2 * t + 1 + (up1 ? 0 : 8)].y;
        uint32_t qs[4][2];
#pragma unroll
        for (int h = 0; h < 4; h++) {
            qs[h][0] = (t >> 1) == (h & 1) ? f[0][5 * (h >> 1) + 2] : 0u; qs[h][1] = (t >> 1) == (h & 1) ? f[1][5 * (h >> 1) + 2] : 0u;
            asm volatile("" : "+r"(qs[h][0]), "+r"(qs[h][1]));
        }
#pragma unroll
        for (int j = 0; j < 10; j++) asm volatile("" : "+r"(f[0][j]), "+r"(f[1][j]), "+r"(f[0][10 + j]));
        if (warp & 3) above(); else if (wg) halo();
        TSTAMP1T(10, 64); CSA(2);
        if (warp && !wg) mbar_wait(bars + 416 + 8 * warp, 0);
        CSA(3);
        float sc[4][3][4];
#pragma unroll
        for (int h = 0; h < 4; h++) {
            const int jb = 5 * (h >> 1) + 3 * (h & 1), js = 5 * (h >> 1) + 2;
#pragma unroll
            for (int nt = 1; nt < 3; nt++) {
#pragma unroll
                for (int e = 0; e < 4; e++) sc[h][nt][e] = 0.f;
                mma_bf16(sc[h][nt], f[0][jb], f[1][jb], f[0][jb + 1], f[1][jb + 1], f[nt - 1][10 + jb], f[nt - 1][11 + jb]);
                mma_bf16_k8(sc[h][nt], qs[h][0], qs[h][1], f[nt - 1][10 + js]);
            }
        }
        if (warp == 0) halo();
        TSTAMP1(8); CSA(4);
#pragma unroll
        for (int h = 0; h < 4; h++) {
            const int jb = 5 * (h >> 1) + 3 * (h & 1), js = 5 * (h >> 1) + 2;
#pragma unroll
            for (int e = 0; e < 4; e++) sc[h][0][e] = 0.f;
            mma_bf16(sc[h][0], f[0][jb], f[1][jb], f[0][jb + 1], f[1][jb + 1], kp[jb], kp[jb + 1]);
            mma_bf16_k8(sc[h][0], qs[h][0], qs[h][1], kp[js]);
        }
        TSTAMP1T(3, 64);
        float p[4][4], sum[4][2];
        uint32_t lg[4][2], mx[4];
        const float rl[4] = {rk[0] * ra, rk[1] * ra, rk[2] * rb, rk[3] * rb};
        auto max2 = [](uint32_t a, uint32_t b) { uint32_t r; asm("max.bf16x2 %0, %1, %2;" : "=r"(r) : "r"(a), "r"(b)); return r; };
#pragma unroll
        for (int h = 0; h < 4; h++) {
            lg[h][0] = pack2((up0 ? sc[h][0][0] : sc[h][1][0]) * rl[0], (up0 ? sc[h][1][2] : sc[h][2][2]) * rl[2]);
            lg[h][1] = pack2((up1 ? sc[h][0][1] : sc[h][1][1]) * rl[1], (up1 ? sc[h][1][3] : sc[h][2][3]) * rl[3]);
            if (edge) {
                if (up0) lg[h][0] = __byte_perm(lg[h][0], 0xce6eu, 0x3254);
                if (up1) lg[h][1] = __byte_perm(lg[h][1], 0xce6eu, 0x3254);
            }
            mx[h] = max2(lg[h][0], lg[h][1]);
        }
#pragma unroll
        for (int o = 1; o <= 2; o <<= 1)
#pragma unroll
            for (int h = 0; h < 4; h++) mx[h] = max2(mx[h], __shfl_xor_sync(~0u, mx[h], o));
#pragma unroll
        for (int h = 0; h < 4; h++)
#pragma unroll
            for (int r = 0; r < 2; r++) {
                const float m = __uint_as_float(r ? mx[h] & 0xffff0000u : mx[h] << 16);
#pragma unroll
                for (int e = 0; e < 2; e++)
                    asm("ex2.approx.ftz.f32 %0, %1;" : "=f"(p[h][2 * r + e]) : "f"((__uint_as_float(r ? lg[h][e] & 0xffff0000u : lg[h][e] << 16) - m) * 1.4426950408889634f));
                sum[h][r] = p[h][2 * r] + p[h][2 * r + 1];
            }
#pragma unroll
        for (int o = 1; o <= 2; o <<= 1)
#pragma unroll
            for (int h = 0; h < 4; h++)
#pragma unroll
                for (int r = 0; r < 2; r++) sum[h][r] += __shfl_xor_sync(~0u, sum[h][r], o);
        TSTAMP1T(5, 64); CSA(5);
        const uint32_t mu = (up0 ? 0xffffu : 0u) | (up1 ? 0xffff0000u : 0u);
        uint32_t ob[10][2];
#pragma unroll
        for (int P = 0; P < 2; P++) {
            float os[2][4];
#pragma unroll
            for (int e = 0; e < 2; e++) {
                const int h = 2 * P + e;
                const float i0 = rcp_apx(sum[h][0]), i1 = rcp_apx(sum[h][1]);
                const uint32_t w0 = pack2(p[h][0] * rk[0] * i0, p[h][1] * rk[1] * i0), w1 = pack2(p[h][2] * rk[2] * i1, p[h][3] * rk[3] * i1);
#pragma unroll
                for (int dt = 0; dt < 3; dt++) {
                    const int j = 5 * P + (dt < 2 ? 3 * e + dt : 2);
                    float o[4] = {0.f, 0.f, 0.f, 0.f};
                    mma_bf16(o, w0 & ~mu, w1 & mu, 0u, w1 & ~mu, vb[j][0], vb[j][1]);
                    mma_bf16_k8(o, w0 & mu, 0u, vp[j]);
                    if (dt < 2) { ob[j][0] = pack2(o[0], o[1]); ob[j][1] = pack2(o[2], o[3]); }
                    else { os[e][0] = o[0]; os[e][1] = o[1]; os[e][2] = o[2]; os[e][3] = o[3]; }
                }
            }
#pragma unroll
            for (int k = 0; k < 4; k++) os[0][k] = t < 2 ? os[0][k] : os[1][k];
            ob[5 * P + 2][0] = pack2(os[0][0], os[0][1]); ob[5 * P + 2][1] = pack2(os[0][2], os[0][3]);
        }
        const uint32_t sl = sbase + (wg ? A1_SM_A1 : A1_SM_A0);
        const uint32_t o0 = (warp & 3) * 2048 + g * 64 + ((t ^ (g >> 1)) << 4), o1 = 8192 + (warp & 3) * 512 + g * 32 + ((t ^ ((g >> 2) << 1)) << 3);
        CSA(15);
        mbar_wait(bar_done, 0);
        if (wg == 0) mbar_wait(bar_kvf, 0);
#pragma unroll
        for (int h = 0; h < 2; h++) {
            asm volatile("st.shared.v4.u32 [%0], {%1,%2,%3,%4};" ::"r"(sl + o0 + h * 1024), "r"(ob[0][h]), "r"(ob[1][h]), "r"(ob[2][h]), "r"(ob[3][h]) : "memory");
            asm volatile("st.shared.v4.u32 [%0], {%1,%2,%3,%4};" ::"r"(sl + o0 + h * 1024 + 512), "r"(ob[4][h]), "r"(ob[5][h]), "r"(ob[6][h]), "r"(ob[7][h]) : "memory");
            asm volatile("st.shared.v2.u32 [%0], {%1,%2};" ::"r"(sl + o1 + h * 256), "r"(ob[8][h]), "r"(ob[9][h]) : "memory");
        }
        if (wg && lane == 0) mbar_arrive(bars + 384 + 8 * warp);
        fence_async_smem();
        __syncwarp();
        TSTAMP1T(4, 64); CSA(6);
        TSTAMP1(1);
        TSTAMP2(1);
        const unsigned char* ot = reinterpret_cast<const unsigned char*>(of) + mb * 163840 + wg * 10240;
        if (lane == 0) {
            asm volatile("cp.async.bulk.global.shared::cta.bulk_group [%0], [%1], 2048;" ::"l"(ot + hg * 20480 + (warp & 3) * 2048), "r"(sl + (warp & 3) * 2048) : "memory");
            asm volatile("cp.async.bulk.global.shared::cta.bulk_group [%0], [%1], 512;" ::"l"(ot + hg * 20480 + 8192 + (warp & 3) * 512), "r"(sl + 8192 + (warp & 3) * 512) : "memory");
            asm volatile("cp.async.bulk.commit_group;" ::: "memory");
            if (wg == 0) mbar_arrive(bar_pv);
            asm volatile("cp.async.bulk.wait_group 0;" ::: "memory");
            asm volatile(A1_FRED " [%0], 1;" ::"l"(reinterpret_cast<uint32_t*>(rsum + 2 * SEQ) + (((layer * 16 + mb) * 2 + wg) * 8 + hg) * FSTR) : "memory");
            DBGC(4 + warp);
        }
        TSTAMP4(11); CSA(7);
        float ac2[40];
        const uint64_t db0 = make_desc(sbase, 1024, 256, 3), db1 = make_desc(sbase + 10240, 512, 256, 3), da0 = make_desc(sl, 16, 1024, 2), da1 = make_desc(sl + 8192, 16, 256, 3);
        const uint32_t o7 = wg ? 640 : (A1_SM_W0 - A1_SM_A0) >> 4;
        const uint32_t trow = ((lane & 7) + 8 * (lane >> 4)) * 128 + (((2 * (warp & 3) + ((lane >> 3) & 1)) ^ (lane & 7)) << 4);
        uint32_t xr[10][2];
        mbar_wait(bar_f2 + 64 * wg + 64, 0);
        if (layer == 0) {
#pragma unroll
            for (int j = 0; j < 10; j += 2) ldsm_x4(&xr[j][0], sl + 51200 + (16 * (warp & 3) + (lane & 15)) * 160 + (lane >> 4) * 16 + 16 * j);
        } else {
#pragma unroll
            for (int j = 0; j < 10; j += 2) ldsm_x4_t(&xr[j][0], sl + 51200 + trow + 1024 * j);
        }
        const uint32_t ri = __shfl_sync(~0u, layer * SEQ + (wg * 2 + ((g >> 1) & 1)) * 512 + (mb * 16 + 4 * (warp & 3) + (g >> 2)) * 2 + (g & 1), lane);
        mbar_wait(bar_wo, 0);
        if (wg) mbar_wait(bar_pv, 0);
        if (wg) asm volatile("bar.sync 2, 128;" ::: "memory"); else asm volatile("bar.sync 1, 128;" ::: "memory");
        TSTAMP2(2); CSA(8);
#pragma unroll
        for (int q = 0; q < 8; q++) {
            uint32_t bo = wo_off(0) >> 4;
            if (q) {
                mbar_wait(bar_f2 + 64 * wg + 8 * q, 0);
                asm volatile("ld.shared.u32 %0, [%1];" : "=r"(bo) : "r"(que + 32 * wg + 4 * q) : "memory");
                bo = __shfl_sync(~0u, bo, 0);
                TSTAMP4(q);
                if (q % 3 == 1) CSA(9 + q / 3);
                if (q == 1 && (tid & 127) == 0) DBGC(29 + 8 * wg);
            }
            wgmma_fence();
#pragma unroll
            for (int j = 0; j < 5; j++) wgmma_n80(ac2, (j < 4 ? da0 : da1) + (q == 7 ? o7 : 0u) + (uint64_t)((q < 6 ? q * 640 : 0) + (j & 2) * 16 + (j & 1) * 2), (j < 4 ? db0 : db1) + bo + (uint64_t)((j & 2) * 160 + (j & 1) * 32), j || q);
            wgmma_commit();
            if (q == 0) {
                wgmma_wait<0>();
                if ((tid & 127) == 0) { mbar_arrive(bar_e2 + 16 * wg); mbar_arrive(bar_e2 + 8); }
            }
            if (q == 2 && wg) {
                wgmma_wait<1>();
                if (tid == 128) mbar_arrive(bar_e2 + 24);
            }
        }
        if ((tid & 127) == 0) DBGC(28 + wg * 8 + 7);
        TSTAMP2(3);
        wgmma_wait<0>();
        TSTAMP2(4); CSA(12);
        if (__any_sync(~0u, ac2[0] != ac2[0] || ac2[2] != ac2[2])) {
#pragma unroll
            for (int i = 0; i < 40; i++) ac2[i] = 0.f;
            uint32_t a[20], an[20];
            auto lda = [&](uint32_t (&r)[20], int h) {
#pragma unroll
                for (int u = 0; u < 4; u++)
                    asm volatile("ld.relaxed.gpu.global.v4.u32 {%0,%1,%2,%3}, [%4];" : "=r"(r[4 * u]), "=r"(r[4 * u + 1]), "=r"(r[4 * u + 2]), "=r"(r[4 * u + 3]) : "l"(ot + h * 20480 + o0 + u * 512) : "memory");
#pragma unroll
                for (int u = 0; u < 2; u++)
                    asm volatile("ld.relaxed.gpu.global.v2.u32 {%0,%1}, [%2];" : "=r"(r[16 + 2 * u]), "=r"(r[17 + 2 * u]) : "l"(ot + h * 20480 + o1 + u * 256) : "memory");
            };
            lda(an, 0);
#pragma unroll 5
            for (int k = lane; k < WOB / 16; k += 32)
                reinterpret_cast<uint4*>(stg + (sl - sbase))[k] = __ldcg(reinterpret_cast<const uint4*>(wo + hg * 8 * WOB) + k);
            __syncwarp();
#pragma unroll 1
            for (int h = 0; h < 8; h++) {
#pragma unroll 1
                for (int it = 0; it < SPIN_MAX; it++) {
                    uint32_t m = 0;
#pragma unroll
                    for (int k = 0; k < 20; k += 2) m = __vimax3_u32(m, an[k], an[k + 1]);
                    if (!__any_sync(~0u, m == ~0u)) break;
                    lda(an, h);
                }
#pragma unroll
                for (int k = 0; k < 20; k++) a[k] = an[k];
                lda(an, min(h + 1, 7));
                const uint32_t bp = h == hg ? sl : sbase + wo_off(h + (h < hg));
                const int r0 = 8 * ((lane & 7) >> 1) + 2 * (lane >> 3) + (lane & 1), r2 = 4 * ((lane & 7) >> 1) + 2 * ((lane >> 3) & 1) + (lane & 1);
#pragma unroll
                for (int n = 0; n < 10; n++) {
                    uint32_t b[12];
                    ldsm_x4_t(b, bp + (n >> 1) * 1024 + r0 * 32 + (((n ^ (r0 >> 2)) & 1) << 4));
                    ldsm_x4_t(b + 4, bp + 5120 + (n >> 1) * 1024 + r0 * 32 + (((n ^ (r0 >> 2)) & 1) << 4));
                    ldsm_x4_t(b + 8, bp + 10240 + (n >> 1) * 512 + r2 * 32 + (((n ^ (r2 >> 2)) & 1) << 4));
                    mma_bf16(ac2 + 4 * n, a[0], a[8], a[1], a[9], b[0], b[1]); mma_bf16(ac2 + 4 * n, a[2], a[10], a[3], a[11], b[2], b[3]);
                    mma_bf16(ac2 + 4 * n, a[4], a[12], a[5], a[13], b[4], b[5]); mma_bf16(ac2 + 4 * n, a[6], a[14], a[7], a[15], b[6], b[7]);
                    mma_bf16(ac2 + 4 * n, a[16], a[18], a[17], a[19], b[8], b[9]);
                }
            }
        }
#pragma unroll
        for (int j = 0; j < 10; j++)
#pragma unroll
            for (int hh = 0; hh < 2; hh++) {
                const uint32_t a = pack2(ac2[4 * j + 2 * hh], ac2[4 * j + 2 * hh + 1]);
                const __nv_bfloat162 r = __hadd2_rn(*reinterpret_cast<const __nv_bfloat162*>(&xr[j][hh]), *reinterpret_cast<const __nv_bfloat162*>(&a));
                xr[j][hh] = *reinterpret_cast<const uint32_t*>(&r);
            }
        const uint32_t so = sl + 30720;
#pragma unroll
        for (int j = 0; j < 10; j += 2) stsm_x4_t(so + trow + 1024 * j, xr[j][0], xr[j][1], xr[j + 1][0], xr[j + 1][1]);
        if (wg) asm volatile("bar.sync 2, 128;" ::: "memory"); else asm volatile("bar.sync 1, 128;" ::: "memory");
        TSTAMP2(5); CSA(13);
        if ((tid & 127) == 0) {
            fence_async_smem();
            asm volatile("cp.async.bulk.tensor.2d.global.shared::cta.bulk_group [%0, {%1, %2}], [%3];" ::"l"(&tmX1), "r"(mb * 128 + 64 * wg), "r"(hg * 80), "r"(so) : "memory");
            asm volatile("cp.async.bulk.commit_group;" ::: "memory");
        }
        __syncwarp();
        const float p0 = *(volatile const float*)&rw[g].x, p1 = *(volatile const float*)&rw[g + 8].x;
        float s[3][4] = {};
        const uint32_t pp[2] = {__byte_perm(__float_as_uint(p0), 0, 0x3232), __byte_perm(__float_as_uint(p1), 0, 0x3232)};
#pragma unroll
        for (int j = 0; j < 10; j += 2) {
            const uint32_t d0 = sub2(xr[j][0], pp[0]), d1 = sub2(xr[j][1], pp[1]), d2 = sub2(xr[j + 1][0], pp[0]), d3 = sub2(xr[j + 1][1], pp[1]);
            mma_bf16(s[0], xr[j][0], xr[j][1], xr[j + 1][0], xr[j + 1][1], 0x3f803f80u, 0x3f803f80u);
            mma_bf16(s[1], d0, d1, d2, d3, d0, d2);
            mma_bf16(s[2], d0, d1, d2, d3, d1, d3);
        }
        if (t == (g >> 1)) {
            float2* rp = rsum + ri;
            asm volatile("red.relaxed.gpu.global.add.v2.f32 [%0], {%1, %2};" ::"l"(rp), "f"(fmaf(-80.f, p0, s[0][0])), "f"((g & 1) ? s[1][1] : s[1][0]) : "memory");
            asm volatile("red.relaxed.gpu.global.add.v2.f32 [%0], {%1, %2};" ::"l"(rp + 4), "f"(fmaf(-80.f, p1, s[0][2])), "f"((g & 1) ? s[2][3] : s[2][2]) : "memory");
        }
        asm volatile("cp.async.bulk.wait_group.read 0;" ::: "memory");
        TSTAMP2(6); CSA(14); CSA_END;
        if (tid == 0) DBGC(63);
        if (tid == 128) DBGC(28);
        if (tid == 0) DBGCAL(2);
        GSTAMP(g_tim1, 14);
        SPAN(1 + 4 * layer, 3);
    }
#undef layer
}

static int h_nsm;
static void* h_sym[11];
static TileTab h_tab[2];
static CUtensorMap h_tmX0, h_tmX1, h_tmR0, h_tmR1, h_tmX1st, h_tmOut;
static KgMaps h_tmW;
typedef CUresult (*PFN_encodeTiled)(CUtensorMap*, CUtensorMapDataType, cuuint32_t, void*, const cuuint64_t*, const cuuint64_t*,
                                    const cuuint32_t*, const cuuint32_t*, CUtensorMapInterleave, CUtensorMapSwizzle,
                                    CUtensorMapL2promotion, CUtensorMapFloatOOBfill);
static void make_tmap(CUtensorMap* tm, const void* ptr, uint64_t cols, uint64_t rows, uint32_t bc, uint32_t br, CUtensorMapSwizzle sw, uint64_t pitch = 0, uint64_t hi = 0, uint32_t bh = 2) {
    static PFN_encodeTiled fn = nullptr;
    if (!fn) {
        void* p = nullptr; cudaDriverEntryPointQueryResult qr;
        cudaGetDriverEntryPoint("cuTensorMapEncodeTiled", &p, cudaEnableDefault, &qr);
        fn = (PFN_encodeTiled)p;
    }
    if (br == 0) {
        cuuint64_t dims[5] = {16, 2, rows / 8, 4, cols / 16}; cuuint64_t strides[4] = {cols * 2, cols * 16, cols * 4, 32};
        cuuint32_t box[5] = {16, 2, bc, 4, 5}; cuuint32_t es[5] = {1, 1, 1, 1, 1};
        fn(tm, CU_TENSOR_MAP_DATA_TYPE_BFLOAT16, 5, const_cast<void*>(ptr), dims, strides, box, es, CU_TENSOR_MAP_INTERLEAVE_NONE, sw,
           CU_TENSOR_MAP_L2_PROMOTION_L2_128B, CU_TENSOR_MAP_FLOAT_OOB_FILL_NONE);
        return;
    }
    if (hi == 16) {
        cuuint64_t dims[4] = {16, 32, 120, 20}; cuuint64_t strides[3] = {3840, 32, 32 * 3840};
        cuuint32_t box[4] = {16, 32, 5, 2}; cuuint32_t es[4] = {1, 1, 1, 1};
        fn(tm, CU_TENSOR_MAP_DATA_TYPE_BFLOAT16, 4, const_cast<void*>(ptr), dims, strides, box, es, CU_TENSOR_MAP_INTERLEAVE_NONE, sw,
           CU_TENSOR_MAP_L2_PROMOTION_L2_128B, CU_TENSOR_MAP_FLOAT_OOB_FILL_NONE);
        return;
    }
    if (bh == 0) {
        cuuint64_t dims[5] = {64, 64, 2, 16, 10}; cuuint64_t strides[4] = {pitch * 2, hi * 2, cols * 2, rows * 2};
        cuuint32_t box[5] = {64, 64, 2, 1, 1}; cuuint32_t es[5] = {1, 1, 1, 1, 1};
        fn(tm, CU_TENSOR_MAP_DATA_TYPE_BFLOAT16, 5, const_cast<void*>(ptr), dims, strides, box, es, CU_TENSOR_MAP_INTERLEAVE_NONE, sw,
           CU_TENSOR_MAP_L2_PROMOTION_L2_128B, CU_TENSOR_MAP_FLOAT_OOB_FILL_NONE);
        return;
    }
    if (hi) {
        cuuint64_t dims[3] = {cols, rows, hi == 64 ? 32u : 2u}; cuuint64_t strides[2] = {pitch * 2, hi * 2};
        cuuint32_t box[3] = {bc, br, bh}; cuuint32_t es[3] = {1, 1, 1};
        fn(tm, CU_TENSOR_MAP_DATA_TYPE_BFLOAT16, 3, const_cast<void*>(ptr), dims, strides, box, es, CU_TENSOR_MAP_INTERLEAVE_NONE, sw,
           CU_TENSOR_MAP_L2_PROMOTION_L2_128B, CU_TENSOR_MAP_FLOAT_OOB_FILL_NONE);
        return;
    }
    cuuint64_t dims[2] = {cols, rows}; cuuint64_t strides[1] = {(pitch ? pitch : cols) * 2};
    cuuint32_t box[2] = {bc, br}; cuuint32_t es[2] = {1, 1};
    fn(tm, CU_TENSOR_MAP_DATA_TYPE_BFLOAT16, 2, const_cast<void*>(ptr), dims, strides, box, es, CU_TENSOR_MAP_INTERLEAVE_NONE, sw,
       CU_TENSOR_MAP_L2_PROMOTION_L2_128B, CU_TENSOR_MAP_FLOAT_OOB_FILL_NONE);
}
template <typename... Args>
static void launch_pdl(void (*kern)(Args...), int grid, int block, int smem, Args... args) {
    cudaLaunchConfig_t cfg = {};
    cfg.gridDim = dim3(grid); cfg.blockDim = dim3(block); cfg.dynamicSmemBytes = smem; cfg.stream = cudaStreamPerThread;
    cudaLaunchAttribute at[1];
    at[0].id = cudaLaunchAttributeProgrammaticStreamSerialization; at[0].val.programmaticStreamSerializationAllowed = 1;
    cfg.attrs = at; cfg.numAttrs = 1;
    cudaLaunchKernelEx(&cfg, kern, args...);
}
static void launch_stage(int k, void* const* d_in, void* d_out) {
    const Par par = {k > 1 ? nullptr : (const bf16*)d_in[4], (const bf16*)d_in[5], (const bf16*)d_in[6], (const bf16*)d_in[7], (const bf16*)d_in[8], (const bf16*)d_in[9], k > 1, 0, (const bf16*)d_in[0],
                     (uint4*)h_sym[4], (uint4*)h_sym[2], (uint4*)h_sym[6], (uint4*)h_sym[3], (uint4*)h_sym[0], (float*)h_sym[5], (uint4*)h_sym[1], (const bf16*)d_in[1], (const bf16*)d_in[2]};
    auto a1 = h_nsm == 132 ? a1_kernel<true> : a1_kernel<false>;
    switch (k) {
        case 1: a1<<<h_nsm, A1_THREADS, A1_SMEM, cudaStreamPerThread>>>(par, h_tmX0, h_tmR0, h_tmX1st, h_tmW, h_tab[0]); break;
        case 3: launch_pdl(conv_kernel, DM / CV_CPB, CV_THREADS, CV_SMEM, 0, (const uint4*)h_sym[7], (const float4*)h_sym[4], (const bf16*)h_sym[8], (bf16*)h_sym[9], (const uint4*)h_sym[0], h_tmOut); break;
        case 5: launch_pdl(a1, h_nsm, A1_THREADS, A1_SMEM, par, h_tmX1, h_tmR1, h_tmX1st, h_tmW, h_tab[1]); break;
        case 7: launch_pdl(conv_kernel, DM / CV_CPB, CV_THREADS, CV_SMEM, 1, (const uint4*)h_sym[7] + SEQ / 8, (const float4*)h_sym[4] + SEQ / 2, (const bf16*)h_sym[8], (bf16*)h_sym[10], (const uint4*)h_sym[0], h_tmOut); break;
        default: break;
    }
}
static int n_stage_kernels() { return 9; }
static const char* stage_name(int k) { const char* n[] = {"kgen", "a1", "a2", "conv", "tr", "a1", "a2", "conv", "tr"}; return n[k]; }

extern "C" void kernel_launch(void* const* d_in, const int* in_sizes, int n_in, void* d_out, int out_size) {
    (void)in_sizes; (void)n_in; (void)out_size;
    static const void *p_in = nullptr, *p_w1 = nullptr, *p_w2 = nullptr, *p_out = nullptr;
    if (p_in != d_in[0] || p_w1 != d_in[1] || p_w2 != d_in[2] || p_out != d_out) {
        cudaFuncSetAttribute(conv_kernel, cudaFuncAttributeMaxDynamicSharedMemorySize, CV_SMEM);
        cudaFuncSetAttribute(a1_kernel<true>, cudaFuncAttributeMaxDynamicSharedMemorySize, A1_SMEM);
        cudaFuncSetAttribute(a1_kernel<false>, cudaFuncAttributeMaxDynamicSharedMemorySize, A1_SMEM);
        int dev; cudaGetDevice(&dev); cudaDeviceGetAttribute(&h_nsm, cudaDevAttrMultiProcessorCount, dev);
        if (h_nsm != 132) h_nsm = 128;
        cudaGetSymbolAddress(&h_sym[0], g_tap); cudaGetSymbolAddress(&h_sym[1], g_wq); cudaGetSymbolAddress(&h_sym[2], g_wo);
        cudaGetSymbolAddress(&h_sym[3], g_halo); cudaGetSymbolAddress(&h_sym[4], g_sum); cudaGetSymbolAddress(&h_sym[5], g_csp); cudaGetSymbolAddress(&h_sym[6], g_of);
        cudaGetSymbolAddress(&h_sym[7], g_piv); cudaGetSymbolAddress(&h_sym[8], g_x1T); cudaGetSymbolAddress(&h_sym[9], g_xcT); cudaGetSymbolAddress(&h_sym[10], g_yT);
        for (int i = 0; i < 264; i++) {
            const int s = i % 132, h = (s - 64) >> 1;
            const int t = h_nsm != 132 ? s : s < 64 ? ((s >> 1) & 7) * 16 + (s >> 4) * 2 + (s & 1) : s < 120 ? (1 + h % 7) * 16 + 8 + (h / 7) * 2 + (s & 1) : s < 124 ? 128 : s - 116;
            const int hg = (4 * (t >> 6) + (t & 3)) & 7;
            const uint64_t wp = (uint64_t)h_sym[1] + hg * 10 * WQ_STAGE;
            h_tab[i / 132].e[s] = make_uint4((uint32_t)wp, (uint32_t)(wp >> 32), ((t >> 2) & 15) | (i / 132) << 4 | hg << 8 | 5 * (hg >> 2) << 16 | (uint32_t)t << 24, 0);
        }
        void *px1, *px2;
        cudaGetSymbolAddress(&px1, g_x1T); cudaGetSymbolAddress(&px2, g_xcT);
        make_tmap(&h_tmX0, d_in[0], 128 * 640, 64, 64, 64, CU_TENSOR_MAP_SWIZZLE_128B, 1280, 640, 0);
        make_tmap(&h_tmX1, px2, 128, 64 * XCP, 64, 64, CU_TENSOR_MAP_SWIZZLE_128B, XCP, 64, 0);
        make_tmap(&h_tmR0, d_in[0], 640, 1024, 80, 64, CU_TENSOR_MAP_SWIZZLE_NONE, 1280, 640, 1);
        make_tmap(&h_tmR1, px2, 64, 640, 64, 80, CU_TENSOR_MAP_SWIZZLE_128B, XCP, 64, 1);
        make_tmap(&h_tmX1st, px1, 2048, 640, 64, 80, CU_TENSOR_MAP_SWIZZLE_128B, XCP);
        make_tmap(&h_tmW.q, d_in[1], 16, 640, 16, 32, CU_TENSOR_MAP_SWIZZLE_32B, 1920, 16, 5);
        make_tmap(&h_tmW.o, d_in[2], 640, 640, 4, 0, CU_TENSOR_MAP_SWIZZLE_32B);
        make_tmap(&h_tmW.t, d_in[2], 640, 640, 2, 0, CU_TENSOR_MAP_SWIZZLE_32B);
        make_tmap(&h_tmOut, d_out, 640, 1024, 80, 8, CU_TENSOR_MAP_SWIZZLE_NONE, 1280, 640, 1);
        p_in = d_in[0]; p_w1 = d_in[1]; p_w2 = d_in[2]; p_out = d_out;
    }
    for (int k = 0; k < n_stage_kernels(); k++) launch_stage(k, d_in, d_out);
}
```

```cpp
#include <cuda_runtime.h>
#include <cuda_bf16.h>
#include <cuda_fp16.h>
#include <stdint.h>
#include <cuda.h>

typedef __nv_bfloat16 bf16;

constexpr int SEQ = 2048;
constexpr int DM = 640;
constexpr int NMODE = 192;

__device__ __forceinline__ float bf2f(bf16 v) { return __bfloat162float(v); }
__device__ __forceinline__ float rbf(float v) {
    uint32_t r;
    asm("cvt.rn.bf16x2.f32 %0, %1, %2;" : "=r"(r) : "f"(v), "f"(0.f));
    return __uint_as_float(r);
}
__device__ __forceinline__ uint32_t pack2(float lo, float hi) {
    __nv_bfloat162 t = __floats2bfloat162_rn(lo, hi);
    return *reinterpret_cast<uint32_t*>(&t);
}
__device__ __forceinline__ void pdl_sync() {
    asm volatile("griddepcontrol.wait;" ::: "memory");
    asm volatile("griddepcontrol.launch_dependents;" ::: "memory");
}
__device__ __forceinline__ float sqrt_apx(float v) { float r; asm("sqrt.approx.ftz.f32 %0, %1;" : "=f"(r) : "f"(v)); return r; }
__device__ __forceinline__ float rcp_apx(float v) { float r; asm("rcp.approx.ftz.f32 %0, %1;" : "=f"(r) : "f"(v)); return r; }
__device__ __forceinline__ uint32_t smem_u32(const void* p) { return (uint32_t)__cvta_generic_to_shared(p); }

constexpr int TAPB = 2944, TAPE = 928;
__device__ __align__(128) uint4 g_tap[DM * TAPB / 16];
#define XPAD 64
constexpr int XCP = SEQ + XPAD;
__device__ __align__(128) bf16 g_x1T[DM * XCP];
__device__ __align__(128) bf16 g_xcT[DM * XCP];
__device__ __align__(128) uint4 g_of[128 * 1280];
constexpr int WQ_STAGE = 240 * 128, WOB = 80 * 160;
__device__ __align__(128) uint4 g_wq[8 * 10 * WQ_STAGE / 16];
__device__ __align__(128) uint4 g_wo[64 * WOB / 16];
__device__ __align__(128) uint4 g_xb[128 * 240];
__device__ __align__(16) float g_csp[10 * 1920];
#define FSTR 32
__device__ __align__(128) float2 g_sum[2 * SEQ + 256 * FSTR];
__device__ __align__(16) bf16 g_piv[2 * SEQ];
__device__ __align__(128) bf16 g_yT[DM * XCP];
__device__ uint32_t g_epoch;
__device__ __align__(16) unsigned long long g_rstat[SEQ];
__device__ __align__(128) uint4 g_halo[640 * 148];
__device__ __forceinline__ unsigned long long tagw(uint32_t payload, uint32_t tag) { return ((unsigned long long)tag << 32) | payload; }
__device__ __forceinline__ ulonglong2 ld_tag2(const ulonglong2* p) {
    ulonglong2 v;
    asm volatile("ld.relaxed.gpu.global.v2.u64 {%0, %1}, [%2];" : "=l"(v.x), "=l"(v.y) : "l"(p) : "memory");
    return v;
}
__device__ __forceinline__ bool tag_ok(ulonglong2 v, uint32_t tag) { return (uint32_t)(v.x >> 32) == tag && (uint32_t)(v.y >> 32) == tag; }
__device__ __forceinline__ uint32_t ld_epoch() { uint32_t v; asm volatile("ld.relaxed.gpu.global.u32 %0, [%1];" : "=r"(v) : "l"(&g_epoch) : "memory"); return v + 1; }
constexpr int SPIN_MAX = 1 << 20;
__device__ __align__(128) uint32_t g_started[11 * 32];
__device__ __forceinline__ void sm_started(int slot) { asm volatile("red.relaxed.gpu.global.add.u32 [%0], 1;" ::"l"(g_started + slot) : "memory"); }
__device__ __forceinline__ void publish(int slot) {
    asm volatile("fence.proxy.async.global;" ::: "memory");
    asm volatile("red.release.gpu.global.add.u32 [%0], 1;" ::"l"(g_started + slot) : "memory");
}
__device__ __forceinline__ void await_all(int slot, uint32_t want) {
#pragma unroll 1
    for (int it = 0; it < SPIN_MAX; it++) {
        uint32_t v;
        asm volatile("ld.acquire.gpu.global.u32 %0, [%1];" : "=r"(v) : "l"(g_started + slot) : "memory");
        if (__all_sync(~0u, (int)(v - want) >= 0)) break;
        __nanosleep(50);
    }
    asm volatile("fence.proxy.async.global;" ::: "memory");
}
__device__ __noinline__ void sm_idle(int slot) {
    if (threadIdx.x != 288) return;
    asm volatile("fence.acq_rel.gpu;" ::: "memory");
    asm volatile("fence.proxy.async.global;" ::: "memory");
    sm_started(slot);
    const uint32_t want = ld_epoch() * gridDim.x;
    pdl_sync();
#pragma unroll 1
    for (int it = 0; it < SPIN_MAX; it++) {
        uint32_t v;
        asm volatile("ld.relaxed.gpu.global.u32 %0, [%1];" : "=r"(v) : "l"(g_started + slot) : "memory");
        if ((int)(v - want) >= 0) break;
        __nanosleep(100);
    }
}
struct TileTab { uint4 e[132]; };
__device__ __forceinline__ bool elect() {
    uint32_t p;
    asm volatile("{\n.reg .pred p;\nelect.sync _|p, 0xffffffff;\nselp.b32 %0, 1, 0, p;\n}" : "=r"(p));
    return p;
}
#define DBG_SYMS
#define TSTAMP(i)
#define TSTAMP1(i)
#define TSTAMP1T(i, t)
#define TSTAMP1X(i, t)
#define SPAN(k, i)
#define GSTAMP(arr, i)
#define TSTAMP2(i)
#define TSTAMP3(i)
#define TSTAMP4(i)
#define TSTAMPK(i, t)
#define TSTAMPC(i)
#define DBGC(i)
#define DBGV(i, v)
#define DBGCAL(i)

#define CSK(i)
#define CSK_END
#define CSA(i)
#define CSA_END
#define CST(i)
#define CST_END
#define CST_EXTRA 0
__device__ __forceinline__ void mma_bf16(float* d, uint32_t a0, uint32_t a1, uint32_t a2, uint32_t a3, uint32_t b0, uint32_t b1) {
    asm volatile("mma.sync.aligned.m16n8k16.row.col.f32.bf16.bf16.f32 {%0,%1,%2,%3}, {%4,%5,%6,%7}, {%8,%9}, {%0,%1,%2,%3};"
                 : "+f"(d[0]), "+f"(d[1]), "+f"(d[2]), "+f"(d[3]) : "r"(a0), "r"(a1), "r"(a2), "r"(a3), "r"(b0), "r"(b1));
}
__device__ __forceinline__ void mma_bf16_k8(float* d, uint32_t a0, uint32_t a1, uint32_t b0) {
    asm volatile("mma.sync.aligned.m16n8k8.row.col.f32.bf16.bf16.f32 {%0,%1,%2,%3}, {%4,%5}, {%6}, {%0,%1,%2,%3};"
                 : "+f"(d[0]), "+f"(d[1]), "+f"(d[2]), "+f"(d[3]) : "r"(a0), "r"(a1), "r"(b0));
}
__device__ __forceinline__ void ldsm_x4(uint32_t* r, uint32_t addr) {
    asm volatile("ldmatrix.sync.aligned.m8n8.x4.shared.b16 {%0,%1,%2,%3}, [%4];"
                 : "=r"(r[0]), "=r"(r[1]), "=r"(r[2]), "=r"(r[3]) : "r"(addr));
}

__device__ __forceinline__ void ldsm_x4_t(uint32_t* r, uint32_t addr) {
    asm volatile("ldmatrix.sync.aligned.m8n8.x4.trans.shared.b16 {%0,%1,%2,%3}, [%4];"
                 : "=r"(r[0]), "=r"(r[1]), "=r"(r[2]), "=r"(r[3]) : "r"(addr));
}
__device__ __forceinline__ void mbar_init(uint32_t bar, int count) { asm volatile("mbarrier.init.shared::cta.b64 [%0], %1;" ::"r"(bar), "r"(count)); }
__device__ __forceinline__ void mbar_arrive(uint32_t bar) { asm volatile("mbarrier.arrive.shared::cta.b64 _, [%0];" ::"r"(bar) : "memory"); }
__device__ __forceinline__ void mbar_wait(uint32_t bar, uint32_t parity) {
    asm volatile("{\n.reg .pred p;\nWAIT_LOOP:\n"
                 "mbarrier.try_wait.parity.shared::cta.b64 p, [%0], %1;\n"
                 "@p bra.uni WAIT_DONE;\nbra.uni WAIT_LOOP;\nWAIT_DONE:\n}" ::"r"(bar), "r"(parity) : "memory");
}

__device__ __forceinline__ void mbar_expect_tx(uint32_t bar, uint32_t bytes) {
    asm volatile("mbarrier.arrive.expect_tx.shared::cta.b64 _, [%0], %1;" ::"r"(bar), "r"(bytes) : "memory");
}
__device__ __forceinline__ void tma_load_2d(uint32_t dst, const void* tmap, int c0, int c1, uint32_t bar) {
    asm volatile("cp.async.bulk.tensor.2d.shared::cluster.global.mbarrier::complete_tx::bytes [%0], [%1, {%3, %4}], [%2];"
                 ::"r"(dst), "l"(tmap), "r"(bar), "r"(c0), "r"(c1) : "memory");
}
__device__ __forceinline__ void tma_load_3d(uint32_t dst, const void* tmap, int c0, int c1, int c2, uint32_t bar) {
    asm volatile("cp.async.bulk.tensor.3d.shared::cluster.global.mbarrier::complete_tx::bytes [%0], [%1, {%3, %4, %5}], [%2];"
                 ::"r"(dst), "l"(tmap), "r"(bar), "r"(c0), "r"(c1), "r"(c2) : "memory");
}
__device__ __forceinline__ void fence_async_smem() { asm volatile("fence.proxy.async.shared::cta;" ::: "memory"); }
__device__ __forceinline__ void bulk_load(uint32_t dst, const void* src, uint32_t bytes, uint32_t bar) {
    asm volatile("cp.async.bulk.shared::cluster.global.mbarrier::complete_tx::bytes [%0], [%1], %2, [%3];"
                 ::"r"(dst), "l"(src), "r"(bytes), "r"(bar) : "memory");
}
__device__ __forceinline__ void stsm_x4(uint32_t addr, uint32_t r0, uint32_t r1, uint32_t r2, uint32_t r3) {
    asm volatile("stmatrix.sync.aligned.m8n8.x4.shared.b16 [%0], {%1,%2,%3,%4};" ::"r"(addr), "r"(r0), "r"(r1), "r"(r2), "r"(r3) : "memory");
}
__device__ __forceinline__ void stsm_x4_t(uint32_t addr, uint32_t r0, uint32_t r1, uint32_t r2, uint32_t r3) {
    asm volatile("stmatrix.sync.aligned.m8n8.x4.trans.shared.b16 [%0], {%1,%2,%3,%4};" ::"r"(addr), "r"(r0), "r"(r1), "r"(r2), "r"(r3) : "memory");
}
__device__ __forceinline__ void prefetch_tmap(const void* tmap) { asm volatile("prefetch.tensormap [%0];" ::"l"(tmap) : "memory"); }

__device__ __forceinline__ float2 cexp_at(float wr2, float wi, float p) {
    float er;
    asm("ex2.approx.ftz.f32 %0, %1;" : "=f"(er) : "f"(wr2 * p));
    float th = wi * p;
    const float k = rintf(th * 0.15915494309189535f);
    th = fmaf(k, -6.2831854820251465f, th);
    th = fmaf(k, 1.7484555314695172e-7f, th);
    return make_float2(er * __cosf(th), er * __sinf(th));
}
__device__ __forceinline__ float2 cmul(float2 a, float2 b) {
    return make_float2(fmaf(a.x, b.x, -a.y * b.y), fmaf(a.x, b.y, a.y * b.x));
}
__device__ __forceinline__ float2 csqr(float2 a) { return make_float2(fmaf(a.x, a.x, -a.y * a.y), (a.x + a.x) * a.y); }
__device__ __forceinline__ uint32_t packh(float2 v) {
    uint32_t r;
    asm("cvt.rn.f16x2.f32 %0, %1, %2;" : "=r"(r) : "f"(v.y), "f"(v.x));
    return r;
}
__device__ __forceinline__ uint2 packr(float2 v) { return make_uint2(packh(v), packh(make_float2(-v.y, v.x))); }
__device__ __forceinline__ uint32_t hcmul(uint32_t a, uint2 b) {
    const __half2 x = *reinterpret_cast<const __half2*>(&a);
    const __half2 r = __hfma2(__high2half2(x), *reinterpret_cast<const __half2*>(&b.y), __hmul2(__low2half2(x), *reinterpret_cast<const __half2*>(&b.x)));
    return *reinterpret_cast<const uint32_t*>(&r);
}

struct Par { const bf16 *logA, *Aim, *Cre, *Cim, *logdt, *dsk; int layer, pad; const bf16* x; uint4 *sum, *wop, *of, *halo, *tap; float* csp; uint4* wq; const bf16 *wqkv, *wo; };
struct KgMaps { CUtensorMap q, o, t; };

__device__ __forceinline__ void bulk_prefetch(const void* p, uint32_t bytes) { asm volatile("cp.async.bulk.prefetch.L2.global [%0], %1;" ::"l"(p), "r"(bytes) : "memory"); }
__device__ __forceinline__ void bulk_store(void* dst, uint32_t src, uint32_t bytes) { asm volatile("cp.async.bulk.global.shared::cta.bulk_group [%0], [%1], %2;" ::"l"(dst), "r"(src), "r"(bytes) : "memory"); }
__device__ __forceinline__ void kgen_first(const Par& in, const KgMaps& tm, const uint32_t b0, const uint32_t wbar, const bool one) {
    const uint32_t blk = blockIdx.x, sec = (blk >= 40) + (blk >= 80), it = (blk >> 3) - 5 * sec, up = (blk >> 2) & 1, hi = blk >> 6;
    auto fetch = [&](int h) {
        if (blk < 120) asm volatile("cp.async.bulk.tensor.4d.shared::cluster.global.mbarrier::complete_tx::bytes [%0], [%1, {%3, %3, %4, %5}], [%2];"
                                    ::"r"(b0 + 10240 * h), "l"(&tm.q), "r"(wbar + 8 * h), "r"(0), "r"(sec * 40 + (blk & 7) * 5), "r"(2 * it + 10 * (up ^ h)) : "memory");
    };
    auto fetch_o = [&](int i) {
        asm volatile("cp.async.bulk.tensor.5d.shared::cluster.global.mbarrier::complete_tx::bytes [%0], [%1, {%3, %3, %4, %3, %5}], [%2];"
                     ::"r"(b0 + 20480 + i * 5120), "l"(&tm.o + i), "r"(wbar + 16), "r"(0), "r"((blk & 7) * 10 + (hi + i) * 4), "r"(((blk >> 3) & 7) * 5) : "memory");
    };
    if (one) {
#pragma unroll
        for (int i = 0; i < 3; i++) mbar_init(wbar + 8 * i, 1);
        asm volatile("fence.mbarrier_init.release.cluster;" ::: "memory");
        fetch(0);
    }
    __syncwarp();
    if (blk >> 20) __trap();
    if (one) {
        bulk_prefetch(in.wqkv + blk * 9600, 19200);
        fetch(1);
        bulk_prefetch(in.wo + blk * 3200, 6400);
        fetch_o(0);
        if (hi) fetch_o(1);
        mbar_expect_tx(wbar, 10240); mbar_expect_tx(wbar + 8, 10240); mbar_expect_tx(wbar + 16, 5120 + hi * 2560);
        bulk_prefetch(in.x + blk * 10240, 20480);
    }
}
__device__ __forceinline__ void kgen_side(const Par& in, const uint32_t b0, const uint32_t wbar) {
    const uint32_t blk = blockIdx.x, sec = (blk >= 40) + (blk >= 80), it = (blk >> 3) - 5 * sec, cg = (blk >> 3) & 7, hb = blk & 7;
    unsigned char* dst = reinterpret_cast<unsigned char*>(in.wq) + (hb * 10 + it) * WQ_STAGE + sec * 5120;
    if (blk < 120) {
        mbar_wait(wbar, 0);
        CSK(2);
        bulk_store(dst, b0, 5120); bulk_store(dst + 15360, b0 + 5120, 5120);
        mbar_wait(wbar + 8, 0);
        CSK(3);
        bulk_store(dst + 5 * WQ_STAGE, b0 + 10240, 5120); bulk_store(dst + 5 * WQ_STAGE + 15360, b0 + 15360, 5120);
        asm volatile("cp.async.bulk.commit_group;" ::: "memory");
        asm volatile("cp.async.bulk.wait_group 0;" ::: "memory");
        CSK(4);
        publish(96 + 32 * hb);
        CSK(5);
    }
    if (blk < 128) {
        mbar_wait(wbar + 16, 0);
        bulk_store(reinterpret_cast<unsigned char*>(in.wop) + (cg * 8 + (hb == cg ? 0 : hb + (hb < cg))) * WOB + (blk >> 6) * 5120, b0 + 20480, blk < 64 ? 5120 : 7680);
        asm volatile("cp.async.bulk.commit_group;" ::: "memory");
    }
}
__device__ __forceinline__ void kgen_sums(const Par& in, const uint32_t b0, const int h) {
    const int lane = threadIdx.x & 31, blk = blockIdx.x;
    if (blk < 120) {
        float cs[5][4] = {};
#pragma unroll
        for (int a = 0; a < 4; a++)
#pragma unroll
            for (int j = 0; j < 5; j++) {
                uint32_t w[4];
                ldsm_x4_t(w, b0 + h * 10240 + j * 1024 + ((lane >> 4) * 8 + (lane & 7)) * 32 + ((((lane >> 3) ^ (lane >> 2)) & 1) << 4) + (a >> 1) * 5120 + (a & 1) * 512);
                mma_bf16(cs[j], w[0], w[1], w[2], w[3], 0x3f803f80u, 0x3f803f80u);
            }
#pragma unroll
        for (int j = 0; j < 5; j++)
            if ((lane & 3) < 2) in.csp[(blk + 120 * h) * 80 + j * 16 + (lane >> 2) + 8 * (lane & 3)] = (lane & 3) ? cs[j][2] : cs[j][0];
    }
}
struct KgPar { uint32_t pw[4], ph[4], pdt, pdsk; };
__device__ __forceinline__ void kgen_load(const Par& in, const bf16* logA, const int w11, KgPar& k) {
    const uint32_t o = blockIdx.x * 480 + min(w11 * 48, w11 * 32 + 128), ow = o + (threadIdx.x & 31), oh = o + ow + (w11 < 8 ? 64 : 0);
    k.pdt = reinterpret_cast<const unsigned short*>(in.logdt)[ow / 96];
    k.pdsk = reinterpret_cast<const unsigned short*>(in.dsk)[ow / 96];
#pragma unroll
    for (int i = 0; i < 4; i++) {
        const bf16* p = i == 0 ? logA : i == 1 ? in.Aim : i == 2 ? in.Cre : in.Cim;
        k.pw[i] = reinterpret_cast<const uint32_t*>(p)[ow]; k.ph[i] = reinterpret_cast<const unsigned short*>(p)[oh];
    }
}
__device__ __forceinline__ void kgen_tables(const Par& in, uint4* tabs, const int w11, const KgPar& kp) {
    const int lane = threadIdx.x & 31, grp = min(w11 >> 1, 4), warp = w11 - 2 * grp;
    const int blk = blockIdx.x, d = blk * 5 + grp, tid = warp * 32 + lane;
    uint4* tab = tabs + grp * (2 * 256);
    const uint32_t *pw = kp.pw, *ph = kp.ph;
#pragma unroll
    for (int i = 0; i < 3; i++)
        if (i < 2 || w11 * 32 + lane < 36) asm volatile("st.global.v4.u32 [%0], {%1,%1,%1,%1};" ::"l"(in.halo + blk * 740 + w11 * 32 + lane + 352 * i), "r"(~0u));
    __syncwarp();
    if (w11 == 10) {
        if (lane < 16) in.sum[blk * 16 + lane] = make_uint4(0, 0, 0, 0);
        else if (lane < 20) reinterpret_cast<uint32_t*>(in.sum + 2048)[(blk * 4 + lane - 16) * FSTR] = 0;
    } else if (w11 > 1) asm volatile("bar.arrive 9, 352;" ::: "memory");
#pragma unroll
    for (int i = 0; i < 6; i++) tabs[w11 * 256 + 32 * i + lane] = make_uint4(0, 0, 0, 0);
    __syncwarp();
    CSK(1);
    const uint32_t tw = smem_u32(tabs) + w11 * 4096;
    const int g = lane >> 2, t = lane & 3;
    const int mt = lane >> 3, r = lane & 7;
    const uint32_t st1 = tw + mt * 1024 + r * 16, st2 = tw + (mt & 1) * 1024 + (mt >> 1) * 128 + ((r ^ (mt >> 1)) << 4), st3 = tw + 2048 + mt * 128 + ((r ^ mt) << 4);
    const uint32_t lda = tw + (mt & 1) * 1024 + r * 128 + (((mt >> 1) ^ r) << 4), ldb = tw + (mt >> 1) * 1024 + r * 128 + (((mt & 1) ^ r) << 4), ldc = tw + 2048 + r * 128 + ((mt ^ r) << 4);
    auto ldsm = [](uint32_t* v, uint32_t a) {
        asm volatile("ldmatrix.sync.aligned.m8n8.x4.shared.b16 {%0,%1,%2,%3}, [%4];" : "=r"(v[0]), "=r"(v[1]), "=r"(v[2]), "=r"(v[3]) : "r"(a) : "memory");
    };
    auto mma = [](float* c, const uint32_t* a, const uint32_t* b) {
        asm("mma.sync.aligned.m16n8k16.row.col.f32.f16.f16.f32 {%0,%1,%2,%3}, {%4,%5,%6,%7}, {%8,%9}, {%0,%1,%2,%3};"
            : "+f"(c[0]), "+f"(c[1]), "+f"(c[2]), "+f"(c[3]) : "r"(a[0]), "r"(a[1]), "r"(a[2]), "r"(a[3]), "r"(b[0]), "r"(b[1]));
    };
    asm volatile("st.shared.u32 [%0], %1;" ::"r"(tw + 3072), "r"(st1 ^ st2 ^ st3 ^ lda ^ ldb ^ ldc) : "memory");
    if (in.pad) __trap();
    const float dt = rbf(expf(__uint_as_float(kp.pdt << 16)));
    const uint32_t cm = __vmaxu2(__vmaxu2(pw[2] & 0x7fff7fffu, pw[3] & 0x7fff7fffu), __byte_perm(ph[2], ph[3], 0x5410) & 0x7fff7fffu);
    const int ex = min(max((int)(__float_as_uint(__uint_as_float(__reduce_max_sync(~0u, max(cm << 16, cm & 0xffff0000u))) * dt) >> 23), 20), 240);
    const float scale = __uint_as_float((uint32_t)(127 + 10 + 127 - ex) << 23), unscale = 2.0f * __uint_as_float((uint32_t)(ex - 10) << 23);
    float k2048 = 0.f;
    float acc[5][4] = {};
    uint32_t af[4][4] = {};
    auto rest = [&] {
        uint32_t b[4][4], c[8];
#pragma unroll
        for (int k = 0; k < 4; k++) {
            ldsm(b[k], ldb ^ (k << 5));
            if (!(k & 1)) ldsm(c + 2 * k, ldc ^ (k << 5));
        }
#pragma unroll
        for (int k = 0; k < 4; k++) { mma(acc[2], af[k], b[k]); mma(acc[3], af[k], b[k] + 2); mma(acc[4], af[k], c + 2 * k); }
    };
#pragma unroll 1
    for (uint32_t sel = 0x1076; sel < (grp < 4 ? 0x6000u : 0x4000u); sel += 0x2200) {
        rest();
        auto par = [&](int i) { return __uint_as_float(__byte_perm(pw[i], ph[i], sel)); };
        const float wr2 = -rbf(expf(par(0))) * dt * 1.4426950408889634f, wi = par(1) * dt;
        const float2 y1 = cexp_at(wr2, -wi, 1.f), w64 = cexp_at(wr2, wi, 64.f), y4 = csqr(csqr(y1)), z8 = csqr(make_float2(y4.x, -y4.y)), y128 = csqr(make_float2(w64.x, -w64.y));
        float2 h0 = make_float2(1.f, 0.f), g0 = make_float2(par(2) * dt * scale, -par(3) * dt * scale);
        const float2 v2 = csqr(y128), v3 = cmul(v2, y128), v4 = csqr(v2), v8 = csqr(v4), c8 = cmul(g0, v8);
        const uint2 z64 = packr(w64), v[8] = {make_uint2(packh(c8), 0u), packr(y128), packr(v2), packr(v3), packr(v4), packr(cmul(v4, y128)), packr(csqr(v3)), packr(cmul(v4, v3))};
        k2048 += fmaf(c8.x, v8.x, -c8.y * v8.y);
        uint32_t ge[4];
#pragma unroll
        for (int e = 0; e < 8; e++) {
            const uint32_t p = packh(h0), q = packh(g0);
            if (!(e & 1)) ge[e >> 1] = q;
            stsm_x4((st1 ^ (e << 4)) + e * 128, p, e ? hcmul(p, z64) : z64.x, q, hcmul(q, v[1]));
            if (e < 7) { h0 = e ? cmul(h0, z8) : z8; g0 = cmul(g0, y1); }
        }
        __syncwarp();
        uint32_t b[4][4];
#pragma unroll
        for (int k = 0; k < 4; k++) { ldsm(af[k], lda ^ (k << 5)); ldsm(b[k], (ldb ^ (k << 5)) + 2048); }
#pragma unroll
        for (int e = 0; e < 8; e += 2) {
            stsm_x4((st2 ^ (e << 4)) + e * 128, hcmul(ge[e & 3], v[2 + (e >> 2)]), hcmul(ge[0], v[4 + (e >> 1)]), hcmul(ge[(e & 3) + 1], v[2 + (e >> 2)]), hcmul(ge[2], v[4 + (e >> 1)]));
            if (!(e & 3)) stsm_x4((st3 ^ (e << 4)) + e * 128, e ? hcmul(v[0].x, v[e]) : v[0].x, hcmul(v[0].x, v[e + 1]), hcmul(v[0].x, v[e + 2]), hcmul(v[0].x, v[e + 3]));
            mma(acc[0], af[e >> 1], b[e >> 1]);
            mma(acc[1], af[e >> 1], b[e >> 1] + 2);
        }
        __syncwarp();
        if (sel == 0x1076) CSK(3);
    }
    rest();
#pragma unroll
    for (int e = 0; e < 5; e++) k2048 += __shfl_xor_sync(~0u, k2048, 1 << e);
    {
        float* Pp = reinterpret_cast<float*>(tab + warp * 256);
        auto sw = [](int i) { return i ^ ((i >> 2) & 24); };
#pragma unroll
        for (int h = 0; h < 2; h++) {
            const int b = g + 8 * h;
            *reinterpret_cast<float2*>(Pp + sw(8 * b + 2 * t)) = make_float2(acc[0][2 * h] * unscale, acc[0][2 * h + 1] * unscale);
            *reinterpret_cast<float2*>(Pp + 128 + sw(8 * b + 2 * t)) = make_float2(acc[1][2 * h] * unscale, acc[1][2 * h + 1] * unscale);
            *reinterpret_cast<float2*>(Pp + 256 + sw(4 * b + 2 * (t & 1) + 64 * (t >> 1))) = make_float2(acc[2][2 * h] * unscale, acc[2][2 * h + 1] * unscale);
            *reinterpret_cast<float2*>(Pp + 384 + sw(2 * b + 32 * t)) = make_float2(acc[3][2 * h] * unscale, acc[3][2 * h + 1] * unscale);
            Pp[512 + sw(b + 32 * t)] = acc[4][2 * h] * unscale;
            Pp[512 + sw(b + 32 * t + 16)] = acc[4][2 * h + 1] * unscale;
        }
        if (lane == 0) Pp[640] = k2048 * unscale;
    }
    CSK(4);
    asm volatile("bar.sync %0, %1;" ::"r"(grp + 4), "r"(grp < 4 ? 64 : 96) : "memory");
    if (warp == 2) return;
    const float* Kp = reinterpret_cast<const float*>(tab);
    auto ksum = [&](int i) -> float { return rbf(Kp[i] + Kp[1024 + i] + (grp < 4 ? 0.f : Kp[2048 + i])); };
    auto ksum2 = [&](int q) -> float2 {
        q ^= (q >> 2) & 12;
        const float2 a = reinterpret_cast<const float2*>(Kp)[q], b = reinterpret_cast<const float2*>(Kp)[512 + q];
        const float2 c = grp < 4 ? make_float2(0.f, 0.f) : reinterpret_cast<const float2*>(Kp)[1024 + q];
        return make_float2(a.x + b.x + c.x, a.y + b.y + c.y);
    };
    {
        uint2* W2 = reinterpret_cast<uint2*>(in.tap + d * (TAPB / 16)) + 8;
        uint2* E4 = W2 + (TAPE - 64) / 8;
        float2 v = ksum2(64 * warp + lane), z = ksum2(64 * warp + 32 + lane), y = ksum2(128 + tid);
        const int q = (96 + tid) ^ (((96 + tid) >> 2) & 6);
        const float4 ua = reinterpret_cast<const float4*>(Kp)[q], uc = reinterpret_cast<const float4*>(Kp)[256 + q], ud = grp < 4 ? make_float4(0.f, 0.f, 0.f, 0.f) : reinterpret_cast<const float4*>(Kp)[512 + q];
        const float4 ub = make_float4(uc.x + ud.x, uc.y + ud.y, uc.z + ud.z, uc.w + ud.w);
        const float s1 = ksum(tid == 31 ? 336 : lane ? 384 : 103), s2 = ksum(tid == 31 ? 512 : tid ? 640 : 231);
        if (tid == 0) v.x += __uint_as_float(kp.pdsk << 16);
        if (tid == 63) y.y -= s1;
        const uint32_t lo = pack2(v.x, v.y), hi = pack2(z.x, z.y), tp = pack2(y.x, y.y);
        uint32_t nl = __shfl_sync(~0u, lo, lane - 1), nh = __shfl_sync(~0u, lane == 31 ? lo : hi, lane - 1), nt = __shfl_sync(~0u, tp, lane + 1);
        if (lane == 0) nl = warp ? __float_as_uint(s1) : 0u;
        if (lane == 31) nt = warp ? 0u : __float_as_uint(s1) >> 16;
        W2[64 * warp + lane] = make_uint2(__byte_perm(lo, nl, 0x7610), __byte_perm(lo, 0, 0x1032));
        W2[64 * warp + lane + 32] = make_uint2(__byte_perm(hi, nh, 0x7610), __byte_perm(hi, 0, 0x1032));
        reinterpret_cast<uint4*>(W2)[64 + tid] = make_uint4(__byte_perm(tp, __float_as_uint(s2), tid ? 0x1010 : 0x7610), __byte_perm(tp, 0, 0x1010), __byte_perm(tp, 0, 0x1032), __byte_perm(nt, tp, 0x7610));
        E4[(tid < 32 ? 159 : 209 - 32) + tid] = make_uint2(pack2(ua.x + ub.x, ua.y + ub.y), pack2(ua.z + ub.z, ua.w + ub.w - (tid == 31 ? s2 : 0.f)));
        if (tid == 63) E4[241] = make_uint2(__float_as_uint(s2) >> 16, 0u);
    }
    CSK(5);
    SPAN(0, 3);
}

#define CV_SLEEP 40
#define CV_LD "ld.relaxed.gpu.global"
#define CV_NL 1
#define CV_D2 3
#define CV_PDH 12
#define CV_PDF 4
#define CV_HAND 7
constexpr int CV_CPB = 5;
constexpr int CV_THREADS = 512;
constexpr int UPADF = 128;
constexpr int ULEN = UPADF + SEQ;
constexpr int XLEN = XCP;
constexpr int BX_5 = 0, BX_3 = 3264, BX_9 = 6528, BX_7 = 8960, BX_LEN = 11392;
constexpr int CV_SM_U = 0;
constexpr int CV_SM_T = CV_CPB * ULEN * 2;
constexpr int CV_SM_B = CV_SM_T + CV_CPB * TAPB;
constexpr int CV_SM_X = CV_SM_B + CV_CPB * BX_LEN;
constexpr int CV_SM_Y = (CV_SM_X + CV_CPB * XLEN * 2 + 127) & ~127;
constexpr int CV_SM_CNT = CV_SM_Y + CV_CPB * 8192;
constexpr int CV_SM_O = CV_SM_CNT + 128;
constexpr int CV_SMEM = CV_SM_O + 20480 + CST_EXTRA;
static_assert(ULEN % 128 == 0 && CV_SM_B % 128 == 0 && CV_SM_CNT % 128 == 0, "layout");

__device__ __forceinline__ uint32_t sub2(uint32_t x, uint32_t m) {
    const __nv_bfloat162 d = __hsub2(*reinterpret_cast<const __nv_bfloat162*>(&x), *reinterpret_cast<const __nv_bfloat162*>(&m));
    return *reinterpret_cast<const uint32_t*>(&d);
}
__device__ __forceinline__ uint32_t add2(uint32_t x, uint32_t y) {
    const __nv_bfloat162 d = __hadd2_rn(*reinterpret_cast<const __nv_bfloat162*>(&x), *reinterpret_cast<const __nv_bfloat162*>(&y));
    return *reinterpret_cast<const uint32_t*>(&d);
}
__device__ __forceinline__ void wgmma_fence() { asm volatile("wgmma.fence.sync.aligned;" ::: "memory"); }
__device__ __forceinline__ void wgmma_commit() { asm volatile("wgmma.commit_group.sync.aligned;" ::: "memory"); }
template <int N> __device__ __forceinline__ void wgmma_wait() { asm volatile("wgmma.wait_group.sync.aligned %0;" ::"n"(N) : "memory"); }
__device__ __forceinline__ uint64_t make_desc(uint32_t addr, uint32_t lbo, uint32_t sbo, uint32_t mode) {
    return (uint64_t)((addr & 0x3FFFF) >> 4) | ((uint64_t)(lbo >> 4) << 16) | ((uint64_t)(sbo >> 4) << 32) | ((uint64_t)mode << 62);
}
__device__ __forceinline__ void wgmma_rs128(float (&d)[64], uint2 hi, uint2 lo, uint64_t db, int acc) {
    asm volatile("{\n.reg .pred p;\nsetp.ne.b32 p, %69, 0;\nwgmma.mma_async.sync.aligned.m64n128k16.f32.bf16.bf16 {%0,%1,%2,%3,%4,%5,%6,%7,%8,%9,%10,%11,%12,%13,%14,%15,%16,%17,%18,%19,%20,%21,%22,%23,%24,%25,%26,%27,%28,%29,%30,%31,%32,%33,%34,%35,%36,%37,%38,%39,%40,%41,%42,%43,%44,%45,%46,%47,%48,%49,%50,%51,%52,%53,%54,%55,%56,%57,%58,%59,%60,%61,%62,%63}, {%64,%65,%66,%67}, %68, p, 1, 1, 0;\n}"
                 : "+f"(d[0]), "+f"(d[1]), "+f"(d[2]), "+f"(d[3]), "+f"(d[4]), "+f"(d[5]), "+f"(d[6]), "+f"(d[7]), "+f"(d[8]), "+f"(d[9]), "+f"(d[10]), "+f"(d[11]), "+f"(d[12]), "+f"(d[13]), "+f"(d[14]), "+f"(d[15]), "+f"(d[16]), "+f"(d[17]), "+f"(d[18]), "+f"(d[19]), "+f"(d[20]), "+f"(d[21]), "+f"(d[22]), "+f"(d[23]), "+f"(d[24]), "+f"(d[25]), "+f"(d[26]), "+f"(d[27]), "+f"(d[28]), "+f"(d[29]), "+f"(d[30]), "+f"(d[31]), "+f"(d[32]), "+f"(d[33]), "+f"(d[34]), "+f"(d[35]), "+f"(d[36]), "+f"(d[37]), "+f"(d[38]), "+f"(d[39]), "+f"(d[40]), "+f"(d[41]), "+f"(d[42]), "+f"(d[43]), "+f"(d[44]), "+f"(d[45]), "+f"(d[46]), "+f"(d[47]), "+f"(d[48]), "+f"(d[49]), "+f"(d[50]), "+f"(d[51]), "+f"(d[52]), "+f"(d[53]), "+f"(d[54]), "+f"(d[55]), "+f"(d[56]), "+f"(d[57]), "+f"(d[58]), "+f"(d[59]), "+f"(d[60]), "+f"(d[61]), "+f"(d[62]), "+f"(d[63])
                 : "r"(hi.x), "r"(hi.y), "r"(lo.x), "r"(lo.y), "l"(db), "r"(acc));
}
template <int V> struct Int { __device__ constexpr operator int() const { return V; } };
__device__ __forceinline__ void sts4(uint32_t a, const uint32_t* v) { asm volatile("st.shared.v4.u32 [%0], {%1,%2,%3,%4};" ::"r"(a), "r"(v[0]), "r"(v[1]), "r"(v[2]), "r"(v[3]) : "memory"); }
__device__ __forceinline__ uint32_t lds1(uint32_t a) { uint32_t v; asm volatile("ld.shared.u32 %0, [%1];" : "=r"(v) : "r"(a) : "memory"); return v; }
__device__ __forceinline__ uint32_t lds1v(uint32_t a) { uint32_t v; asm volatile("ld.volatile.shared.u32 %0, [%1];" : "=r"(v) : "r"(a) : "memory"); return v; }
__device__ __forceinline__ uint4 lds4(uint32_t a) { uint4 v; asm volatile("ld.shared.v4.u32 {%0,%1,%2,%3}, [%4];" : "=r"(v.x), "=r"(v.y), "=r"(v.z), "=r"(v.w) : "r"(a) : "memory"); return v; }
__device__ __forceinline__ uint4 ldx(uint32_t a) {
    uint4 v;
    asm volatile("ld.shared.v2.u32 {%0,%1}, [%4];\nld.shared.v2.u32 {%2,%3}, [%4+128];" : "=r"(v.x), "=r"(v.y), "=r"(v.z), "=r"(v.w) : "r"(a) : "memory");
    return v;
}
__device__ __forceinline__ void cv_store(unsigned char* p, uint4 x, uint4 y) {
    asm volatile("st.relaxed.gpu.global.v2.u32 [%0], {%1,%2};" ::"l"(p), "r"(add2(x.x, __byte_perm(y.x, y.y, 0x5410))), "r"(add2(x.y, __byte_perm(y.z, y.w, 0x5410))) : "memory");
    asm volatile("st.relaxed.gpu.global.v2.u32 [%0], {%1,%2};" ::"l"(p + 128), "r"(add2(x.z, __byte_perm(y.x, y.y, 0x7632))), "r"(add2(x.w, __byte_perm(y.z, y.w, 0x7632))) : "memory");
}
__device__ __forceinline__ int usw(int ch) { return ch ^ ((ch >> 3) & 1); }
__global__ void __launch_bounds__(CV_THREADS, 1) conv_kernel(int layer, const uint4* __restrict__ piv, const float4* __restrict__ sum, const bf16* __restrict__ x1T,
                                                             bf16* __restrict__ dst, const uint4* __restrict__ tap, const __grid_constant__ CUtensorMap tmOut) {
    extern __shared__ __align__(1024) unsigned char sm[];
    SPAN(3 + 4 * layer, 0);
    bf16* Us = reinterpret_cast<bf16*>(sm + CV_SM_U);
    bf16* Xs = reinterpret_cast<bf16*>(sm + CV_SM_X);
#define CV_IDX int tid; asm volatile("mov.u32 %0, %tid.x;" : "=r"(tid)); const int lane = tid & 31, warp = __shfl_sync(~0u, tid >> 5, 0);
    const int d0 = blockIdx.x * CV_CPB, tile = blockIdx.x; (void)tile;
    const uint32_t cnt = smem_u32(sm + CV_SM_CNT);
    struct Lc { uint32_t a4, a8, uc, ud, y, e4, en, sp, ss; int go; };
    auto lane_consts = [&](int lane, int c) {
        const int mat = lane >> 3, r = lane & 7, g = lane >> 2, ti = lane & 3, e = g - 2 * ti;
        const int j2 = 13 + (r ^ 1) + 8 * (mat >> 1), j3 = j2 + 2, i0 = 8 * (mat & 1);
        const uint32_t sb = smem_u32(sm), oc = sb + usw(16 * (mat >> 1) + 2 * r + (mat & 1)) * 16;
        const Lc l = {sb + CV_SM_B + c * BX_LEN + ((j2 & 1) ? BX_3 + (4 * j2 + i0 + 84) * 2 : BX_5 + (4 * j2 + i0 + 80) * 2),
                      sb + CV_SM_B + c * BX_LEN + ((j3 & 1) ? BX_7 : BX_9) + (8 * j3 + i0 + 136) * 2,
                      oc + CV_SM_U + (c * ULEN + UPADF) * 2, sb + CV_SM_U + (c * ULEN + UPADF) * 2 + usw(16 * mat + 2 * r + 2) * 16, oc + CV_SM_Y + c * 8192,
                      sb + CV_SM_T + c * TAPB + TAPE + (307 + 2 * g - ti) * 4, sb + CV_SM_T + c * TAPB + (528 + e) * 4,
                      e == -5 ? 0x4410u : e == -4 ? 0x1044u : 0x4444u, e == 3 ? 0x4410u : e == 4 ? 0x1044u : 0x4444u,
                      c * XCP * 2 + (lane >> 4) * 256 + (lane & 15) * 8};
        asm volatile("st.shared.u32 [%0], %1;" ::"r"(sb + CV_SM_CNT + 120), "r"(l.y ^ l.a4 ^ l.a8 ^ l.uc ^ l.ud ^ l.e4 ^ l.en ^ l.sp ^ l.ss ^ l.go) : "memory");
        return l;
    };
    unsigned char* const dq = reinterpret_cast<unsigned char*>(dst + (size_t)d0 * XCP);
    auto far = [&](auto T0_, const auto& seq, const Lc& lc, int c, int lane, const uint2 (&f)[20], uint32_t kk) {
        constexpr int T0 = T0_, T1 = T0 + 6, TC = T0 > 7 ? T0 : 7, NS = sizeof(seq) / sizeof(seq[0]), PD = T0 > 7 ? CV_PDH : CV_PDF;
        uint32_t bq[28], yw[4], yz[4], P, S;
        uint4 xv, yv;
        asm("prmt.b32 %0, %1, 0, %2;" : "=r"(P) : "r"(kk), "r"(lc.sp));
        asm("prmt.b32 %0, %1, 0, %2;" : "=r"(S) : "r"(kk), "r"(lc.ss));
#pragma unroll
        for (int k = 0; 2 * k < T1 - TC + 4; k++) ldsm_x4(bq + 4 * k, lc.uc + (TC - 8) * 256 + 512 * k);
#pragma unroll
        for (int k = 0; 4 * k < T1 - TC; k++) ldsm_x4(bq + 20 + 4 * k, lc.ud + (TC - 8) * 256 + 1024 * k);
        CST(3);
        mbar_wait(cnt + 8 * c, 0);
        mbar_wait(cnt + 40, 0);
        CST(4);
        float acc[6][4] = {};
        uint32_t a[PD + 1][4];
#pragma unroll
        for (int i = -PD; i < NS + 3; i++) {
            if (i + PD < NS) ldsm_x4_t(a[(i + PD) % (PD + 1)], seq[i + PD] < 32 ? lc.a4 + (seq[i + PD] - 2) * 128 : lc.a8 + (seq[i + PD] - 34) * 256);
            if (i < 0) continue;
#pragma unroll
            for (int T = T0; T < T1; T++) {
                if (i >= NS) break;
                const int ee = seq[i] < 32 ? 2 * T - 6 - seq[i] : T + 35 - seq[i];
                if (i == 0 && T >= TC) mma_bf16(acc[T - T0], P, 0u, S, P, bq[2 * (T - TC)], bq[2 * (T - TC) + 1]);
                if (i == 1 && T >= TC) mma_bf16_k8(acc[T - T0], 0u, S, bq[20 + T - TC]);
                if (i == (T >= TC ? 2 : 0)) mma_bf16(acc[T - T0], f[19].x, 0u, f[19].y, f[19].x, bq[2 * (T - TC + 4)], bq[2 * (T - TC + 4) + 1]);
                if (seq[i] < 32 ? ee >= 0 && ee <= 9 : ee >= 10) mma_bf16(acc[T - T0], a[i % (PD + 1)][0], a[i % (PD + 1)][1], a[i % (PD + 1)][2], a[i % (PD + 1)][3], f[ee].x, f[ee].y);
            }
#pragma unroll
            for (int k = 0; k < 3; k++) {
                const int o = 256 * T0 + 512 * k;
                auto at = [&](int d) { return i - d >= 0 && i - d < NS && seq[i - d < 0 ? 0 : i - d < NS ? i - d : 0] == 2 * T0 + 4 * k - 4; };
                if (at(CV_D2)) {
                    cv_store(dq + lc.go + o, xv, yv);
                    if (layer > 19 - 2 * k) __trap();
                }
                if (at(-2)) { ldsm_x4_t(yw, lc.y + o); ldsm_x4_t(yz, lc.y + 3584 + o); }
                if (at(1)) {
#pragma unroll
                    for (int q = 0; q < 4; q++) yw[q] = add2(add2(yw[q], yz[q]), pack2(acc[2 * k + (q >> 1)][2 * (q & 1)], acc[2 * k + (q >> 1)][2 * (q & 1) + 1]));
                    stsm_x4_t(lc.y + o, yw[0], yw[1], yw[2], yw[3]);
                    xv = ldx(smem_u32(Xs) + lc.go + o);
                    __syncwarp();
                    yv = lds4(smem_u32(sm + CV_SM_Y) + c * 8192 + o + usw(lane) * 16);
                    if (layer > 20 - 2 * k) __trap();
                    if (k == 2) CST(6);
                }
            }
        }
    };
    TSTAMP1X(9, 256);
    if (threadIdx.x >= 256) {
        if (threadIdx.x < 288 && elect()) {
            mbar_init(cnt + 48, 1);
            asm volatile("fence.mbarrier_init.release.cluster;" ::: "memory");
            bulk_load(smem_u32(sm + CV_SM_T), tap + d0 * (TAPB / 16), CV_CPB * TAPB, cnt + 48);
            mbar_expect_tx(cnt + 48, CV_CPB * TAPB);
        }
        CV_IDX
        const int wgu = (warp >> 2) & 1, g = lane >> 2, ti = lane & 3;
        CST(1);
        if (warp > 8 && elect()) {
            if (warp < 15) mbar_init(cnt + 8 * (warp - 9), warp == 14 ? 8 : 4);
            else if (layer) prefetch_tmap(&tmOut);
        }
        if (warp < 13 && lane < 17 - (warp == 12)) {
            const int off = warp == 12 ? CV_SM_U : CV_SM_B + (warp == 11 ? BX_7 : (warp - 8) * BX_3), str = warp == 12 ? ULEN * 2 : BX_LEN;
#pragma unroll
            for (int c = 0; c < CV_CPB; c++) *reinterpret_cast<uint4*>(sm + off + c * str + 16 * lane) = make_uint4(0, 0, 0, 0);
        }
        fence_async_smem();
        asm volatile("bar.arrive 3, 512;" ::: "memory");
        asm volatile("bar.sync 1, 256;" ::: "memory");
        TSTAMP1X(10, 256);
        asm volatile("setmaxnreg.inc.sync.aligned.u32 168;");
        const uint32_t Tc = smem_u32(sm + CV_SM_T) + (16 + 128 * (warp & 2) + 8 * (warp & 1) + g - 2 * ti) * 4;
        uint2 fa[8][2], fn[8][2];
        auto near_taps = [&](uint2 (&f)[8][2], int c) {
#pragma unroll
            for (int m = 0; m < 16; m++) f[m >> 1][m & 1] = make_uint2(lds1v(Tc + c * TAPB + 64 * (m >> 1) - 32 * (m & 1)), lds1v(Tc + c * TAPB + 64 * (m >> 1) - 32 * (m & 1) + 512));
        };
        CST(6);
        mbar_wait(cnt + 48, 0);
        TSTAMP1X(11, 256); CST(5);
        near_taps(fa, 3 * wgu);
        near_taps(fn, 2 - wgu);
        const int hc = wgu ? warp & 3 : 4;
        const Lc lc = lane_consts(lane, hc);
        TSTAMP1X(12, 256); CST(0);
        uint32_t ya = smem_u32(sm + CV_SM_Y) + wgu * 8192 + (warp & 2) * 2048 + usw(2 * lane + (warp & 1)) * 16;
        uint64_t db = make_desc(smem_u32(Us + wgu * ULEN + UPADF), 16, 256, 3);
        if (wgu) { asm volatile("bar.sync 6, 384;" ::: "memory"); fence_async_smem(); }
        int c = wgu;
        auto chain = [&](const uint2 (&f)[8][2], auto&& meanwhile) {
            float acc[64];
            asm volatile("bar.sync %0, %1;" ::"r"(c ? 4 + wgu : 2), "r"(c ? 256 : 384) : "memory");
            TSTAMPC(1 + 3 * c);
            if (c < 2) CST(7);
            if (c == 0) fence_async_smem();
            wgmma_fence();
#pragma unroll
            for (int m = 0; m < 8; m++) {
                wgmma_rs128(acc, f[m][0], f[m][1], db - (uint64_t)(2 * m), m);
                if (m == CV_HAND && c < 4) asm volatile("bar.arrive %0, 256;" ::"r"(5 - wgu) : "memory");
            }
            wgmma_commit();
            asm volatile("griddepcontrol.launch_dependents;" ::: "memory");
            TSTAMPC(2 + 3 * c); CST(13 + (c >> 1));
            meanwhile();
            wgmma_wait<0>();
            TSTAMPC(3 + 3 * c); CST(10 + (c >> 1));
            uint32_t w[16];
#pragma unroll
            for (int j = 0; j < 16; j++) w[j] = j ? pack2(acc[4 * j] + acc[4 * j - 2], acc[4 * j + 1] + acc[4 * j - 1]) : pack2(acc[0], acc[1]);
#pragma unroll
            for (int j = 0; j < 16; j += 4) stsm_x4_t(ya + 256 * j, w[j], w[j + 1], w[j + 2], w[j + 3]);
            __syncwarp();
            if (lane == 0) mbar_arrive(cnt + 8 * c);
            c += 2; ya += 16384; db += ULEN / 4;
        };
        const uint32_t e4 = lc.e4, e8 = e4 + 428 - 4 * g;
        uint2 fl[4];
        uint32_t kk;
#pragma unroll 1
        for (;;) {
            if (c != 1) chain(fa, [&] {
                if (c == 3 || warp + c == 12) {
#pragma unroll
                    for (int k = 0; k < 19; k++) (k < 16 ? fn[(k >> 1) & 7][k & 1] : fl[k & 3]) = make_uint2(lds1(k < 10 ? e4 + 32 * k + 16 : e8 + 32 * k - 304), lds1(k < 10 ? e4 + 32 * k : e8 + 32 * k - 320));
                    fl[3] = make_uint2(lds1(lc.en), lds1(lc.en - 32));
                    kk = lds1(smem_u32(sm + CV_SM_T) + TAPB * hc + TAPE + 1672);
                }
            });
            if (c > 4) break;
            if (c == 2) { asm volatile("bar.sync 7, 384;" ::: "memory"); fence_async_smem(); }
            chain(fn, [&] { if (c == 2) near_taps(fa, 4); });
        }
        TSTAMP1X(6, 256); CST(2);
        if (wgu || warp == 8) {
            constexpr int seq[29] = {5, 6, 32, 7, 33, 8, 34, 9, 35, 10, 36, 11, 12, 13, 14, 15, 16, 17, 37, 18, 38, 19, 20, 21, 39, 22, 40, 23, 24};
            uint2 f[20];
#pragma unroll
            for (int k = 0; k < 20; k++) f[k] = k < 16 ? fn[(k >> 1) & 7][k & 1] : fl[k & 3];
            far(Int<10>(), seq, lc, hc, lane, f, kk);
        }
    } else {
        asm volatile("setmaxnreg.dec.sync.aligned.u32 88;");
        CV_IDX
        CST(5);
        const uint4* ppv = piv + tid;
        const float4* psv = sum + tid;
        const uint2* pxv = reinterpret_cast<const uint2*>(x1T + (size_t)d0 * XCP) + (tid >> 4) * 32 + (tid & 15);
        asm volatile("st.shared.u64 [%0], %1;" ::"r"(smem_u32(sm + CV_SM_O) + tid * 16), "l"((uint64_t)ppv ^ (uint64_t)psv ^ (uint64_t)pxv) : "memory");
        const int tc = (0x04302100 >> (4 * warp)) & 7;
        const Lc lc = lane_consts(lane, tc);
        pdl_sync();
        SPAN(3 + 4 * layer, 1);
        TSTAMP(0); CST(0);
        if (tid == 0) TSTAMPC(0);
        if (threadIdx.x == 0) { GSTAMP(g_tim, 15); }
        float4 sv[4];
        uint4 pv;
#pragma unroll
        for (int k = 0; k < 4; k++)
            asm volatile(CV_LD ".v4.f32 {%0,%1,%2,%3}, [%4];" : "=f"(sv[k].x), "=f"(sv[k].y), "=f"(sv[k].z), "=f"(sv[k].w) : "l"(psv + 256 * k) : "memory");
        asm volatile(CV_LD ".v4.u32 {%0,%1,%2,%3}, [%4];" : "=r"(pv.x), "=r"(pv.y), "=r"(pv.z), "=r"(pv.w) : "l"(ppv) : "memory");
        uint2 xe[CV_CPB], xo[CV_CPB];
#pragma unroll
        for (int c = 0; c < CV_NL; c++) {
            asm volatile(CV_LD ".v2.u32 {%0,%1}, [%2];" : "=r"(xe[c].x), "=r"(xe[c].y) : "l"(pxv + c * (XCP / 4)) : "memory");
            asm volatile(CV_LD ".v2.u32 {%0,%1}, [%2];" : "=r"(xo[c].x), "=r"(xo[c].y) : "l"(pxv + c * (XCP / 4) + 16) : "memory");
        }
#define CV_XD 300
#define CV_XW 0
        if (warp == CV_XW) {
            if (elect()) {
                const uint32_t c0 = clock();
                mbar_init(cnt + 56, 1);
                asm volatile("fence.mbarrier_init.release.cluster;" ::: "memory");
                mbar_expect_tx(cnt + 56, CV_CPB * 4096);
                while (clock() - c0 < CV_XD) ;
#pragma unroll
                for (int c = CV_NL; c < CV_CPB + CV_NL; c++) bulk_load(smem_u32(Xs + (c % CV_CPB) * XLEN), x1T + (size_t)(d0 + c % CV_CPB) * XCP, 4096, cnt + 56);
            }
            __syncwarp();
            CST(15);
        }
        constexpr float idm = 1.0f / DM;
        uint32_t mw[4];
        float rs[8];
#pragma unroll
        for (int k = 0; k < 4; k++) {
            const uint32_t pw = k == 0 ? pv.x : k == 1 ? pv.y : k == 2 ? pv.z : pv.w;
            mw[k] = pack2(fmaf(sv[k].x, idm, __uint_as_float(pw << 16)), fmaf(sv[k].z, idm, __uint_as_float(pw & 0xffff0000u)));
            uint32_t vr;
            asm("cvt.rn.relu.bf16x2.f32 %0, %1, %2;" : "=r"(vr) : "f"(fmaf(sv[k].z * -idm, sv[k].z, sv[k].w) * idm), "f"(fmaf(sv[k].x * -idm, sv[k].x, sv[k].y) * idm));
            const uint32_t ve = pack2(__uint_as_float(vr << 16) + 1e-5f, __uint_as_float(vr & 0xffff0000u) + 1e-5f);
            const uint32_t sd = pack2(sqrt_apx(__uint_as_float(ve << 16)), sqrt_apx(__uint_as_float(ve & 0xffff0000u)));
            rs[2 * k] = rcp_apx(__uint_as_float(sd << 16)); rs[2 * k + 1] = rcp_apx(__uint_as_float(sd & 0xffff0000u));
        }
        if (rs[0] != 123.f) TSTAMP(13);
        const uint32_t ua = smem_u32(Us) + usw(tid + UPADF / 8) * 16;
        uint32_t uw[CV_CPB][4];
#pragma unroll
        for (int c = 0; c < CV_CPB; c++) {
            if (c == CV_NL) {
                if (warp == CV_XW) { mbar_wait(cnt + 56, 0); CST(7); }
                asm volatile("bar.sync 10, 256;" ::: "memory");
            }
            if (c == 1 || c == 2) {
#pragma unroll
                for (int k = c; k < (c == 1 ? 2 : CV_CPB); k++) {
 const uint4 v = ldx(smem_u32(Xs + k * XLEN) + (tid >> 4) * 256 + (tid & 15) * 8); xe[k] = make_uint2(v.x, v.y); xo[k] = make_uint2(v.z, v.w); }
            }
            const uint32_t e0 = sub2(xe[c].x, mw[0]), e1 = sub2(xe[c].y, mw[1]), o0 = sub2(xo[c].x, mw[2]), o1 = sub2(xo[c].y, mw[3]);
            uw[c][0] = pack2(__uint_as_float(e0 << 16) * rs[0], __uint_as_float(o0 << 16) * rs[4]); uw[c][1] = pack2(__uint_as_float(e0 & 0xffff0000u) * rs[1], __uint_as_float(o0 & 0xffff0000u) * rs[5]);
            uw[c][2] = pack2(__uint_as_float(e1 << 16) * rs[2], __uint_as_float(o1 << 16) * rs[6]); uw[c][3] = pack2(__uint_as_float(e1 & 0xffff0000u) * rs[3], __uint_as_float(o1 & 0xffff0000u) * rs[7]);
            asm volatile("st.shared.v4.u32 [%0], {%1,%2,%3,%4};" ::"r"(ua + c * ULEN * 2), "r"(uw[c][0]), "r"(uw[c][1]), "r"(uw[c][2]), "r"(uw[c][3]) : "memory");
            if (c < 2) {
                asm volatile("bar.arrive %0, 384;" ::"r"(2 + 4 * c) : "memory");
                if (layer > 29 - c) __trap();
                CST(11 + c);
            }
        }
        asm volatile("bar.arrive 7, 384;" ::: "memory");
        asm volatile("bar.sync 3, 512;" ::: "memory");
        TSTAMP(1); CST(1);
        {
            auto box = [&](auto c0, auto c1, int chunk, int cb, bool full) {
                const uint32_t ea = smem_u32(Us + cb * ULEN) + usw(chunk + UPADF / 8 + (lane ? 1 : -1)) * 16, bx = smem_u32(sm + CV_SM_B + cb * BX_LEN) + chunk * 16;
                uint32_t lo[CV_CPB][4], hi[CV_CPB][2];
#pragma unroll
                for (int c = c0; c < c1; c++) {
                    lo[c][0] = 0;
#pragma unroll
                    for (int k = 1; k < 4; k++) lo[c][k] = __shfl_up_sync(~0u, uw[c][k], 1);
#pragma unroll
                    for (int k = 0; k < 2; k++) hi[c][k] = __shfl_down_sync(~0u, uw[c][k], 1);
                }
#pragma unroll
                for (int c = c0; c < c1; c++)
                    asm volatile("{\n.reg .pred p, q;\nsetp.eq.s32 p, %7, 0;\nsetp.eq.s32 q, %7, 31;\n@p ld.shared.v4.u32 {%0,%1,%2,%3}, [%6];\n@q ld.shared.v2.u32 {%4,%5}, [%6];\n}"
                                 : "+r"(lo[c][0]), "+r"(lo[c][1]), "+r"(lo[c][2]), "+r"(lo[c][3]), "+r"(hi[c][0]), "+r"(hi[c][1]) : "r"(ea + c * ULEN * 2), "r"(lane) : "memory");
#pragma unroll
                for (int c = c0; c < c1; c++) {
                    const uint32_t e[9] = {lo[c][1], lo[c][2], lo[c][3], uw[c][0], uw[c][1], uw[c][2], uw[c][3], hi[c][0], hi[c][1]};
                    uint32_t o[8], p[8], t[7], b3[5], b5[7];
#pragma unroll
                    for (int i = 0; i < 8; i++) { o[i] = __byte_perm(e[i], e[i + 1], 0x5432); p[i] = add2(e[i], o[i]); }
#pragma unroll
                    for (int i = 0; i < 5; i++) b3[i] = add2(o[i], p[i + 1]);
                    sts4(bx + c * BX_LEN + BX_3 + 160, b3);
#pragma unroll
                    for (int i = 1; i < 7; i++) { t[i] = add2(p[i], p[i + 1]); b5[i] = add2(t[i], e[i + 2]); }
                    sts4(bx + c * BX_LEN + BX_5 + 160, b5 + 2);
                    if (full) {
#pragma unroll
                        for (int i = 1; i < 5; i++) { b3[i] = add2(b3[i], t[i + 2]); t[i] = add2(t[i], b5[i + 2]); }
                        sts4(bx + c * BX_LEN + BX_7 + 272, b3 + 1);
                        sts4(bx + c * BX_LEN + BX_9 + 272, t + 1);
                    }
                }
            };
            auto reload = [&](int c, uint32_t a) { const uint4 v = lds4(a); uw[c][0] = v.x; uw[c][1] = v.y; uw[c][2] = v.z; uw[c][3] = v.w; };
            if (warp >= 6) {
#pragma unroll
                for (int c = 0; c < 3; c++) reload(c, ua - 1024 + (c + 2) * ULEN * 2);
            }
            if (warp >= 4) {
#pragma unroll
                for (int c = 3; c < 5; c++) reload(c, ua - 2048 + c * ULEN * 2);
            }
            box(Int<0>(), Int<3>(), warp < 6 ? tid : tid - 64, warp < 6 ? 0 : 2, warp < 4);
            if (warp >= 4) box(Int<3>(), Int<5>(), tid - 128, 0, true);
            else if (tid >= 128 - CV_CPB) {
                const int c = 127 - tid;
                const uint2 v = *reinterpret_cast<const uint2*>(Us + c * ULEN + UPADF);
                const float s1 = __uint_as_float(v.x << 16), s2 = s1 + __uint_as_float(v.x & 0xffff0000u), s3 = s2 + __uint_as_float(v.y << 16), s4 = s3 + __uint_as_float(v.y & 0xffff0000u);
                unsigned char* bc = sm + CV_SM_B + c * BX_LEN;
                *reinterpret_cast<uint32_t*>(bc + BX_5 + 156) = pack2(s1, s2);
                *reinterpret_cast<uint2*>(bc + BX_7 + 264) = make_uint2(v.x << 16, pack2(s2, s3));
                *reinterpret_cast<uint2*>(bc + BX_9 + 264) = make_uint2(pack2(s1, s2), pack2(s3, s4));
            }
        }
        __syncwarp();
        if (lane == 0) mbar_arrive(cnt + 40);
        TSTAMP(2); CST(2);
        if (layer && blockIdx.x == 0 && tid == 224) g_epoch = ld_epoch();
        __syncwarp();
        if ((0x6e >> warp) & 1) {
            constexpr int seq[16] = {0, 1, 2, 3, 4, 5, 6, 32, 7, 8, 9, 33, 10, 34, 11, 12};
            uint2 f[20];
            mbar_wait(cnt, 0);
            const uint32_t e8 = lc.e4 + 428 - (lane & 28);
#pragma unroll
            for (int k = 0; k < 13; k++) f[k] = make_uint2(lds1(k < 10 ? lc.e4 + 32 * k + 16 : e8 + 32 * k - 304), lds1(k < 10 ? lc.e4 + 32 * k : e8 + 32 * k - 320));
            f[19] = make_uint2(lds1(lc.en), lds1(lc.en - 32));
            far(Int<4>(), seq, lc, tc, lane, f, lds1(smem_u32(sm + CV_SM_T) + TAPB * tc + TAPE + 1672));
        }
    }
    {
        CV_IDX
        if ((0xc91 >> warp) & 1) {
            const int c = __popc(0xc91 & ((1 << warp) - 1));
            uint4 xv[2], yv[2];
#pragma unroll
            for (int k = 0; k < 2; k++) xv[k] = ldx(smem_u32(Xs + c * XLEN) + 512 * k + (lane >> 4) * 256 + (lane & 15) * 8);
            const uint32_t u0 = lds1(smem_u32(Us + c * ULEN) + (lane == 31 ? UPADF * 2 : 0));
            mbar_wait(cnt + 8 * c, 0);
#pragma unroll
            for (int k = 0; k < 2; k++) yv[k] = lds4(smem_u32(sm + CV_SM_Y) + c * 8192 + 512 * k + usw(lane) * 16);
            const uint4 yz = lds4(smem_u32(sm + CV_SM_Y) + c * 8192 + 4096 + usw(lane) * 16);
            const float kk = __uint_as_float(lds1(smem_u32(sm + CV_SM_T) + TAPB * c + TAPE + 1272) << 16);
            yv[1].x = add2(yv[1].x, yz.x); yv[1].y = add2(yv[1].y, yz.y); yv[1].z = add2(yv[1].z, yz.z);
            yv[1].w = pack2(fmaf(kk, __uint_as_float(u0 << 16), __uint_as_float(yv[1].w << 16) + __uint_as_float(yz.w << 16)),
                            fmaf(kk, __uint_as_float(u0 << 16) + __uint_as_float(u0 & 0xffff0000u), __uint_as_float(yv[1].w & 0xffff0000u) + __uint_as_float(yz.w & 0xffff0000u)));
#pragma unroll
            for (int k = 0; k < 2; k++) cv_store(dq + c * XCP * 2 + (lane >> 4) * 256 + (lane & 15) * 8 + 512 * k, xv[k], yv[k]);
        }
        TSTAMP(4); CST(8);
        if (layer == 1) {
            const int rb = (blockIdx.x >> 3) + (warp & 8) * 2, cg = blockIdx.x & 7, ch = (tid >> 3) & 31;
            const bf16* src = dst + (size_t)(cg * 80 + ch) * XCP + rb * 64 + (tid & 7) * 8;
            uint32_t v[3][4];
            __syncthreads();
            if (warp & 8) { const uint32_t c0 = clock(); while (clock() - c0 < 300) ; }
            uint32_t todo = (warp & 4) ? 3 : 7;
#pragma unroll 1
            for (int it = 0; it < SPIN_MAX; it++) {
#pragma unroll
                for (int k = 0; k < 3; k++)
                    if (todo >> k & 1)
                        asm volatile("ld.relaxed.gpu.global.v4.u32 {%0,%1,%2,%3}, [%4];" : "=r"(v[k][0]), "=r"(v[k][1]), "=r"(v[k][2]), "=r"(v[k][3]) : "l"(src + k * (32 * XCP)) : "memory");
#pragma unroll
                for (int k = 0; k < 3; k++)
                    if ((todo >> k & 1) && v[k][0] != ~0u && v[k][1] != ~0u && v[k][2] != ~0u && v[k][3] != ~0u) {
                        *reinterpret_cast<uint4*>(sm + (32 * k + ch) * 272 + ((tid & 7) + (warp & 8)) * 16) = make_uint4(v[k][0], v[k][1], v[k][2], v[k][3]);
                        todo ^= 1u << k;
                    }
                if (!todo) break;
                __nanosleep(CV_SLEEP);
            }
            __syncwarp();
            asm volatile("bar.sync %0, 256;" ::"r"(8 + (warp >> 3)) : "memory");
            uint32_t w[12];
#pragma unroll
            for (int k = 0; k < 3; k++) ldsm_x4(&w[4 * k], smem_u32(sm) + min(32 * k + lane, 79) * 272 + warp * 16);
            const uint32_t ot = smem_u32(sm + CV_SM_O) + warp * 1280, oa = ot + (lane & 7) * 160 + (lane >> 3) * 16;
            stsm_x4_t(oa, w[0], w[1], w[2], w[3]);
            stsm_x4_t(oa + 64, w[4], w[5], w[6], w[7]);
            asm volatile("stmatrix.sync.aligned.m8n8.x2.trans.shared.b16 [%0], {%1,%2};" ::"r"(oa + 128), "r"(w[8]), "r"(w[9]) : "memory");
            fence_async_smem();
            __syncwarp();
            if (lane == 0) {
                asm volatile("cp.async.bulk.tensor.3d.global.shared::cta.bulk_group [%0, {%1, %2, %3}], [%4];" ::"l"(&tmOut), "r"(cg * 80), "r"((rb >> 1) * 64 + 8 * (warp & 7)), "r"(rb & 1), "r"(ot) : "memory");
                asm volatile("cp.async.bulk.commit_group;" ::: "memory");
                asm volatile("cp.async.bulk.wait_group.read 0;" ::: "memory");
            }
        }
    }
    TSTAMP(3); CST(9); CST_END;
    GSTAMP(g_tim, 14);
    SPAN(3 + 4 * layer, 3);
}

template <int TA, int TB>
__device__ __forceinline__ void wgmma_n240(float (&d)[120], uint64_t da, uint64_t db, int acc) {
    asm volatile("{\n.reg .pred p;\nsetp.ne.b32 p, %124, 0;\nwgmma.mma_async.sync.aligned.m64n240k16.f32.bf16.bf16 {%0,%1,%2,%3,%4,%5,%6,%7,%8,%9,%10,%11,%12,%13,%14,%15,%16,%17,%18,%19,%20,%21,%22,%23,%24,%25,%26,%27,%28,%29,%30,%31,%32,%33,%34,%35,%36,%37,%38,%39,%40,%41,%42,%43,%44,%45,%46,%47,%48,%49,%50,%51,%52,%53,%54,%55,%56,%57,%58,%59,%60,%61,%62,%63,%64,%65,%66,%67,%68,%69,%70,%71,%72,%73,%74,%75,%76,%77,%78,%79,%80,%81,%82,%83,%84,%85,%86,%87,%88,%89,%90,%91,%92,%93,%94,%95,%96,%97,%98,%99,%100,%101,%102,%103,%104,%105,%106,%107,%108,%109,%110,%111,%112,%113,%114,%115,%116,%117,%118,%119}, %120, %121, p, 1, 1, %122, %123;\n}"
                 : "+f"(d[0]), "+f"(d[1]), "+f"(d[2]), "+f"(d[3]), "+f"(d[4]), "+f"(d[5]), "+f"(d[6]), "+f"(d[7]), "+f"(d[8]), "+f"(d[9]), "+f"(d[10]), "+f"(d[11]), "+f"(d[12]), "+f"(d[13]), "+f"(d[14]), "+f"(d[15]), "+f"(d[16]), "+f"(d[17]), "+f"(d[18]), "+f"(d[19]), "+f"(d[20]), "+f"(d[21]), "+f"(d[22]), "+f"(d[23]), "+f"(d[24]), "+f"(d[25]), "+f"(d[26]), "+f"(d[27]), "+f"(d[28]), "+f"(d[29]), "+f"(d[30]), "+f"(d[31]), "+f"(d[32]), "+f"(d[33]), "+f"(d[34]), "+f"(d[35]), "+f"(d[36]), "+f"(d[37]), "+f"(d[38]), "+f"(d[39]), "+f"(d[40]), "+f"(d[41]), "+f"(d[42]), "+f"(d[43]), "+f"(d[44]), "+f"(d[45]), "+f"(d[46]), "+f"(d[47]), "+f"(d[48]), "+f"(d[49]), "+f"(d[50]), "+f"(d[51]), "+f"(d[52]), "+f"(d[53]), "+f"(d[54]), "+f"(d[55]), "+f"(d[56]), "+f"(d[57]), "+f"(d[58]), "+f"(d[59]), "+f"(d[60]), "+f"(d[61]), "+f"(d[62]), "+f"(d[63]), "+f"(d[64]), "+f"(d[65]), "+f"(d[66]), "+f"(d[67]), "+f"(d[68]), "+f"(d[69]), "+f"(d[70]), "+f"(d[71]), "+f"(d[72]), "+f"(d[73]), "+f"(d[74]), "+f"(d[75]), "+f"(d[76]), "+f"(d[77]), "+f"(d[78]), "+f"(d[79]), "+f"(d[80]), "+f"(d[81]), "+f"(d[82]), "+f"(d[83]), "+f"(d[84]), "+f"(d[85]), "+f"(d[86]), "+f"(d[87]), "+f"(d[88]), "+f"(d[89]), "+f"(d[90]), "+f"(d[91]), "+f"(d[92]), "+f"(d[93]), "+f"(d[94]), "+f"(d[95]), "+f"(d[96]), "+f"(d[97]), "+f"(d[98]), "+f"(d[99]), "+f"(d[100]), "+f"(d[101]), "+f"(d[102]), "+f"(d[103]), "+f"(d[104]), "+f"(d[105]), "+f"(d[106]), "+f"(d[107]), "+f"(d[108]), "+f"(d[109]), "+f"(d[110]), "+f"(d[111]), "+f"(d[112]), "+f"(d[113]), "+f"(d[114]), "+f"(d[115]), "+f"(d[116]), "+f"(d[117]), "+f"(d[118]), "+f"(d[119])
                 : "l"(da), "l"(db), "n"(TA), "n"(TB), "r"(acc));
}

__device__ __forceinline__ void wgmma_n80(float (&d)[40], uint64_t da, uint64_t db, int acc) {
    asm volatile("{\n.reg .pred p;\nsetp.ne.b32 p, %42, 0;\nwgmma.mma_async.sync.aligned.m64n80k16.f32.bf16.bf16 {%0,%1,%2,%3,%4,%5,%6,%7,%8,%9,%10,%11,%12,%13,%14,%15,%16,%17,%18,%19,%20,%21,%22,%23,%24,%25,%26,%27,%28,%29,%30,%31,%32,%33,%34,%35,%36,%37,%38,%39}, %40, %41, p, 1, 1, 0, 1;\n}"
                 : "+f"(d[0]), "+f"(d[1]), "+f"(d[2]), "+f"(d[3]), "+f"(d[4]), "+f"(d[5]), "+f"(d[6]), "+f"(d[7]), "+f"(d[8]), "+f"(d[9]), "+f"(d[10]), "+f"(d[11]), "+f"(d[12]), "+f"(d[13]), "+f"(d[14]), "+f"(d[15]), "+f"(d[16]), "+f"(d[17]), "+f"(d[18]), "+f"(d[19]), "+f"(d[20]), "+f"(d[21]), "+f"(d[22]), "+f"(d[23]), "+f"(d[24]), "+f"(d[25]), "+f"(d[26]), "+f"(d[27]), "+f"(d[28]), "+f"(d[29]), "+f"(d[30]), "+f"(d[31]), "+f"(d[32]), "+f"(d[33]), "+f"(d[34]), "+f"(d[35]), "+f"(d[36]), "+f"(d[37]), "+f"(d[38]), "+f"(d[39])
                 : "l"(da), "l"(db), "r"(acc));
}

constexpr int A1_THREADS = 384;
constexpr int A1_NST = 4;
#define A1_SKEW 8
constexpr int A1_STAGE = 16384 + WQ_STAGE;
constexpr int A1_KVP = 336;
constexpr int A1_SM_KV = 2 * A1_STAGE;
constexpr int A1_SM_END = A1_NST * A1_STAGE;
constexpr int A1_SM_BAR = A1_SM_END + 3072 + 3 * WOB + 64;
constexpr int A1_SM_RS = A1_SM_END + 512;
constexpr int A1_SM_W0 = A1_SM_END + 3072, A1_SM_W3 = A1_SM_END - 3 * WOB, A1_SM_A1 = 2 * WOB, A1_SM_A0 = A1_SM_A1 + 61440;
constexpr int A1_SM_XA = A1_SM_W0 + 2 * WOB, A1_SM_XB = A1_SM_XA + 2048;
constexpr int A1_SMEM = A1_SM_BAR + 512 + 7 * CST_EXTRA / 4;
static_assert(A1_SM_W3 >= A1_SM_KV + 144 * A1_KVP && A1_SM_W3 % 512 == 0 && A1_SM_A1 % 1024 == 0 && A1_SM_A0 <= A1_SM_KV && A1_SM_A0 + 61440 <= A1_SM_W3 && A1_SMEM <= 232448 && 11 * 4096 <= A1_STAGE, "layout");
__device__ __forceinline__ constexpr uint32_t wo_off(int h) { return h * WOB + (h < 3 ? A1_SM_W0 : h < 6 ? A1_SM_W3 - 3 * WOB : -6 * WOB); }
#define A1_FRED "red.relaxed.gpu.global.add.u32"
#define A1_FLD "ld.acquire.gpu.global.u32"
#define ST_SLEEP 20
#define ST_SLEEP0 300
#define A1_P0 2
#define A1_PW (kb - 2)
#define A1_FSPIN SPIN_MAX
#define A1_FSLEEP 40
#define YT_LAYER 1
#define WOT 11
#define A1_WOAT 6

template <int L>
__device__ __forceinline__ void a1_mainloop(float (&acc)[120], uint32_t sbase, uint32_t bars, int wg, int tile) {
    constexpr int layer = L; (void)layer;
    const uint64_t da0 = L ? make_desc(sbase + wg * 8192, 8192, 1024, 1) : make_desc(sbase + wg * 8192, 16, 1024, 1), db0 = make_desc(sbase + 16384, 1024, 256, 3);
#pragma unroll 1
    for (int t = 0;; t++) {
        const int st = t % A1_NST;
        mbar_wait(bars + 8 * st, (t / A1_NST) & 1);
        if (t == A1_SKEW && wg == 0) mbar_wait(bars + 160, 0);
        TSTAMP3(1 + t);
        if (t == 0) CSA(0);
        wgmma_fence();
#pragma unroll
        for (int kk = 0; kk < 4; kk++) wgmma_n240<L, 1>(acc, da0 + (uint32_t)(st * (A1_STAGE / 16) + kk * (L ? 128 : 2)), db0 + (uint32_t)(st * (A1_STAGE / 16) + (kk >> 1) * (WQ_STAGE / 32) + (kk & 1) * 32), kk ? 1 : t);
        wgmma_commit();
        if (t == 9) break;
        if (t == A1_SKEW - 1 && wg == 0) wgmma_wait<0>(); else wgmma_wait<1>();
        if (t > 0 && (threadIdx.x & 127) == 0) {
            if (t != A1_SKEW || wg) mbar_arrive(bars + 8 * (A1_NST + (t - 1) % A1_NST));
            if (t == A1_SKEW - 1 && wg == 0) mbar_arrive(bars + 8 * (A1_NST + t % A1_NST));
        }
    }
}

template <bool MAP>
__global__ void __launch_bounds__(A1_THREADS, 1) a1_kernel(const __grid_constant__ Par in, const __grid_constant__ CUtensorMap tmX, const __grid_constant__ CUtensorMap tmR,
                                                           const __grid_constant__ CUtensorMap tmX1, const __grid_constant__ KgMaps tmW, const __grid_constant__ TileTab tab) {
#define layer in.layer
    const unsigned char* const wo = reinterpret_cast<const unsigned char*>(in.wop);
    float2* const rsum = reinterpret_cast<float2*>(in.sum);
    uint4* const of = in.of;
    extern __shared__ __align__(1024) unsigned char stg[];
    const uint32_t sbase = smem_u32(stg);
    const uint32_t bars = sbase + A1_SM_BAR;
    const uint32_t bar_stat = bars + 64, bar_kv = bars + 72, bar_rd = bars + 168;
    const uint32_t bar_wo = bars + 208, bar_done = bars + 216, bar_pv = bars + 224, bar_kvf = bars + 232, bar_f2 = bars + 248, bar_e2 = bars + 384, que = bars + 448;
    const int tid = threadIdx.x;
    CSK(0);
    const int w = __shfl_sync(~0u, tid >> 5, 0), wg = w >> 2;
    uint32_t smid;
    asm volatile("mov.u32 %0, %smid;" : "=r"(smid));
    const uint4 tv = tab.e[(MAP ? smid : blockIdx.x) + (tid & (smid >> 12))];
    const uint64_t pa = reinterpret_cast<const uint64_t*>(&in)[tid & (smid >> 12)], pb = reinterpret_cast<const uint64_t*>(&in)[6 + (tid & (smid >> 12))];
    const bool one = elect();
    uint32_t tz;
    const unsigned char* wq;
    auto entry = [&] { tz = __shfl_sync(~0u, tv.z, 0); wq = (const unsigned char*)(((uint64_t)__shfl_sync(~0u, tv.y, 0) << 32) | __shfl_sync(~0u, tv.x, 0)); };
    auto issue_w = [&](unsigned it) { bulk_load(sbase + (it % A1_NST) * A1_STAGE + 16384, wq + it * WQ_STAGE, WQ_STAGE, bars + 8 * (it % A1_NST)); };
    auto issue_x = [&](unsigned it, int kb) {
        asm volatile("cp.async.bulk.tensor.5d.shared::cluster.global.mbarrier::complete_tx::bytes [%0], [%1, {%3, %3, %3, %4, %5}], [%2];"
                     ::"r"(sbase + (it % A1_NST) * A1_STAGE), "l"(&tmX), "r"(bars + 8 * (it % A1_NST)), "r"(0), "r"(tz & 15), "r"(kb) : "memory");
    };
    auto first_x = [&] {
        issue_x(0, (tz >> 16) & 7); issue_x(1, ((tz >> 16) & 7) + 1);
    };
    auto expect = [&] {
#pragma unroll
        for (int i = 0; i < A1_NST; i++) mbar_expect_tx(bars + 8 * i, A1_STAGE);
    };
    if (w == 8) {
        if (one) {
            prefetch_tmap(&tmX); prefetch_tmap(&tmW.q);
#pragma unroll
            for (int i = 0; i < A1_NST; i++) mbar_init(bars + 8 * i, 1);
            asm volatile("fence.mbarrier_init.release.cluster;" ::: "memory");
        }
        __syncwarp();
        asm volatile("bar.arrive 0, 384;" ::: "memory");
        if (smid >> 12) __trap();
        entry();
        if ((tz & 0x80000010u) == 16) {
            if (one) {
                issue_w(0);
                asm volatile("griddepcontrol.wait;" ::: "memory");
                first_x();
                issue_w(1);
                expect();
                asm volatile("griddepcontrol.launch_dependents;" ::: "memory");
            }
#pragma unroll
            for (int kb = 2; kb < A1_NST; kb++) {
                __syncwarp();
                mbar_wait(bars + 8 * (kb - 2), 0);
                if (one) { issue_x(kb, ((tz >> 16) & 7) + kb); issue_w(kb); }
                CSK(6 + kb);
            }
        }
        __syncwarp();
        if (!(tz & 16) && blockIdx.x < 128) kgen_first(in, tmW, sbase + A1_SM_W0, bars - 24, one);
        __syncwarp();
    }
    if (w > 8) CSK(8);
    const bool gen = w != 8 && in.logA && blockIdx.x < 128;
    KgPar kp;
    const int w11 = w < 8 ? 2 * (w & 3) + (w >> 2) : w - 1;
    if (gen) kgen_load(in, reinterpret_cast<const bf16*>(pa), w11, kp);
    if (w > 8) CSK(9);
    if (w == 8) {
        const int tile = tz >> 24, mb = tz & 15, hg = (tz >> 8) & 7, kb0 = (tz >> 16) & 7;
        const unsigned l1 = (tz >> 4) & 1;
        if (__builtin_expect(!l1, 0)) {
            CSK(1);
            const uint32_t ep = ld_epoch();
            if (one) {
                kgen_side(in, sbase + A1_SM_W0, bars - 24);
                if (tile < 128) { first_x(); expect(); }
                asm volatile("cp.async.bulk.wait_group 0;" ::: "memory");
            }
            __syncwarp();
            asm volatile("bar.arrive 10, 96;" ::: "memory");
            CSK(6);
            if (tile < 128) {
                await_all(96 + 32 * hg, ep * 15);
                if (one) issue_w(0);
                __syncwarp();
                mbar_wait(bars, 0);
                if (one) { issue_w(1); issue_x(2, kb0 + 2); issue_w(2); }
            }
            CSK(7);
            asm volatile("bar.sync 3, 384;" ::: "memory");
            if (tile < 128 && one) {
                fence_async_smem();
                issue_x(3, kb0 + 3); issue_w(3);
                mbar_expect_tx(bars + 240, 20480);
                bulk_load(sbase + A1_SM_W0, in.x + (size_t)(mb * 128 + hg * 16) * DM, 20480, bars + 240);
            }
            __syncwarp();
            CSK(9);
        } else asm volatile("bar.sync 3, 64;" ::: "memory");
        if (tile < 128 && elect()) {
#pragma unroll 1
            for (unsigned kb = A1_NST; kb < 10; kb++) {
                mbar_wait(bars + 8 * (A1_NST + kb % A1_NST), ((kb / A1_NST) - 1) & 1);
                if (l1 && kb < 9) mbar_wait(bar_rd + 8 * (kb - A1_NST), 0);
                mbar_expect_tx(bars + 8 * (kb % A1_NST), A1_STAGE);
                issue_x(kb, kb < 5 ? kb + kb0 : kb - kb0); issue_w(kb);
                if (kb == (l1 ? A1_WOAT : 9)) {
                    if (!l1) { mbar_wait(bar_stat, 0); asm volatile("fence.proxy.async.global;" ::: "memory"); }
                    mbar_expect_tx(bar_wo, 8 * WOB);
                    bulk_load(sbase + A1_SM_W0, wo + hg * 8 * WOB, 2 * WOB, bar_wo);
                }
            }
            mbar_wait(bars + 8 * (A1_NST + 3), 1);
            bulk_load(sbase + A1_SM_W3, wo + (hg * 8 + 3) * WOB, 3 * WOB, bar_wo);
        }
        CSA(4); CSA_END;
        return;
    }
    {
        if (w < 8 && one) {
#pragma unroll 1
            for (uint32_t c = (w & 4 ? w & 2 ? 0x1111112'01111111ull : 0x1111111'01111184ull : w & 2 ? 0x3122222'01111111ull : 0x1111132'02220000ull) >> (32 * (w & 1)), b = bars + 56 * w; c; c >>= 4, b += 8)
                if (c & 15) mbar_init(b, c & 15);
            asm volatile("fence.mbarrier_init.release.cluster;" ::: "memory");
        }
        __syncwarp();
        asm volatile("bar.sync 0, 384;" ::: "memory");
        if (layer) {
            if (w == 9) asm volatile("bar.arrive 3, 64;" ::: "memory");
        } else {
            if (gen) { SPAN(0, 0); SPAN(0, 1); kgen_tables(in, reinterpret_cast<uint4*>(stg + 3 * A1_STAGE), w11, kp); }
            else if (w != 11 && w11 > 1) asm volatile("bar.arrive 9, 352;" ::: "memory");
            __syncwarp();
            if (w11 < 2) {
                asm volatile("bar.sync 10, 96;" ::: "memory");
                kgen_sums(in, sbase + A1_SM_W0, w11);
                __syncwarp();
                asm volatile("bar.arrive 9, 352;" ::: "memory");
                CSK(1);
            }
            if (w == 9) asm volatile("bar.sync 3, 384;" ::: "memory"); else asm volatile("bar.arrive 3, 384;" ::: "memory");
        }
    }
    tz = __shfl_sync(~0u, tv.z + (uint32_t)(pb >> 32), 0);
    const int tile = tz >> 24, mb = tz & 15, hg = (tz >> 8) & 7;
    float2* rst = reinterpret_cast<float2*>(stg + A1_SM_RS) + 8;
    if (wg == 2) {
        if (w == 11 && layer == 0) {
            asm volatile("bar.sync 9, 352;" ::: "memory");
            CSK(5);
            if (one) publish(64);
            __syncwarp();
            CSK(6);
        }
        if (tile >= 128) { sm_idle(layer); return; }
        if (w == 10) {
            if (one) { prefetch_tmap(&tmR); prefetch_tmap(&tmX1); }
            uint32_t ns;
            asm volatile("mov.u32 %0, %nsmid;" : "=r"(ns));
            if (MAP && ns != 132) __trap();
        }
        __syncwarp();
        if (w == 9) {
            if (layer && one) {
                mbar_expect_tx(bar_stat, 3840);
                bulk_load(sbase + A1_SM_XB, g_xb + tile * 240, 3840, bar_stat);
            }
            __syncwarp();
            uint4* pre = of + (mb * 8 + hg) * 1280 + (tid - 288);
#pragma unroll 1
            for (int k = 0; k < 5 + 5 * layer; k++) {
#pragma unroll
                for (int i = 0; i < 8; i++) asm volatile("st.global.v4.u32 [%0], {%1,%1,%1,%1};" ::"l"(pre + 32 * i), "r"(~0u) : "memory");
                pre += k < 5 ? 256 : XCP / 8;
                if (k == 4) {
                    CSA(2);
                    asm volatile("fence.acq_rel.gpu;" ::: "memory");
                    asm volatile("fence.proxy.async.global;" ::: "memory");
                    __syncwarp();
                    if (tid == 288) mbar_arrive(bar_done);
                    CSA(3);
                    pre = reinterpret_cast<uint4*>(g_yT) + tile * (5 * XCP / 8) + (tid - 288);
                }
            }
            if (layer == 0) {
                asm volatile("griddepcontrol.launch_dependents;" ::: "memory");
                await_all(64, ld_epoch() * gridDim.x);
                CSA(5);
                float4 a[2] = {};
#pragma unroll
                for (int k = 0; k < 10; k++)
#pragma unroll
                    for (int h = 0; h < 2; h++) {
                        const int c4 = min(tid - 288 + 32 * h, 59);
                        const float4 v = __ldcg(reinterpret_cast<const float4*>(g_csp + (k / 5) * 9600 + (k % 5) * 640 + hg * 80) + c4 + (c4 / 20) * 780);
                        a[h].x += v.x; a[h].y += v.y; a[h].z += v.z; a[h].w += v.w;
                    }
#pragma unroll
                for (int h = 0; h < 2; h++)
#pragma unroll
                    for (int k = 0; k < 4; k++) {
                        const float c = 0.5f * (k == 0 ? a[h].x : k == 1 ? a[h].y : k == 2 ? a[h].z : a[h].w), c1 = c - rbf(c), c2 = c1 - rbf(c1);
                        *reinterpret_cast<uint4*>(stg + A1_SM_XB + (4 * min(tid - 288 + 32 * h, 59) + k) * 16) = make_uint4(pack2(c, c1), pack2(c2, 0.f), 0u, 0u);
                    }
                fence_async_smem();
                __syncwarp();
                if (one) {
                    bulk_store(g_xb + tile * 240, sbase + A1_SM_XB, 3840);
                    asm volatile("cp.async.bulk.commit_group;" ::: "memory");
                    asm volatile("cp.async.bulk.wait_group.read 0;" ::: "memory");
                    mbar_arrive(bar_stat);
                }
                __syncwarp();
                CSA(1);
            }
            TSTAMP1T(9, 288);
        } else {
            const int j = tid - 320;
            const uint32_t tag = ld_epoch();
            if (tid == 352) sm_started(layer);
            const int ch = j & 7, kg = (j >> 3) & 3;
            const unsigned char* src = stg + (layer ? (j >> 5) * 8192 + (hg & 3) * 2048 : A1_SM_W0 + (j >> 2) * 1280);
            const int of0 = layer ? kg * 128 + ((ch ^ kg) << 4) : (j & 7) << 4, ofx = layer ? 576 : 64, ofy = layer ? 1024 : 128;
            float s[8], q[8], p0[8];
#pragma unroll
            for (int i = 0; i < 8; i++) { s[i] = 0.f; q[i] = 0.f; }
#pragma unroll 1
            for (int it = 0; it < 5; it++) {
                uint4 v[4];
                mbar_wait(layer ? bars + 8 * (it % A1_NST) : bars + 240, layer * it / A1_NST);
#pragma unroll
                for (int k = 0; k < 4; k++) v[k] = *reinterpret_cast<const uint4*>(src + (layer ? (it % A1_NST) * A1_STAGE : it * 256) + (k & 1 ? of0 ^ ofx : of0) + (k >> 1) * ofy);
                if (it == 0) {
                    const uint4 pv = *reinterpret_cast<const uint4*>(src + (layer ? ch << 4 : 0));
                    const uint32_t w[4] = {pv.x, pv.y, pv.z, pv.w};
#pragma unroll
                    for (int i = 0; i < 4; i++) { p0[2 * i] = __uint_as_float((layer ? w[i] : w[0]) << 16); p0[2 * i + 1] = __uint_as_float(layer ? w[i] & 0xffff0000u : w[0] << 16); }
                }
                asm volatile("" :: "r"(v[0].x), "r"(v[1].x), "r"(v[2].x), "r"(v[3].x), "f"(p0[0]) : "memory");
                __syncwarp();
                if ((tid & 31) == 0) mbar_arrive(bar_rd + 8 * it);
#pragma unroll
                for (int k = 0; k < 4; k++) {
                    const uint32_t w[4] = {v[k].x, v[k].y, v[k].z, v[k].w};
#pragma unroll
                    for (int i = 0; i < 4; i++) {
                        const float a = __uint_as_float(w[i] << 16) - p0[2 * i], b = __uint_as_float(w[i] & 0xffff0000u) - p0[2 * i + 1];
                        s[2 * i] += a; s[2 * i + 1] += b; q[2 * i] = fmaf(a, a, q[2 * i]); q[2 * i + 1] = fmaf(b, b, q[2 * i + 1]);
                    }
                }
            }
            float o[4];
            int row;
            if (layer == 0) {
                float s0 = ((s[0] + s[1]) + (s[2] + s[3])) + ((s[4] + s[5]) + (s[6] + s[7])), q0 = ((q[0] + q[1]) + (q[2] + q[3])) + ((q[4] + q[5]) + (q[6] + q[7]));
#pragma unroll
                for (int o = 1; o <= 2; o <<= 1) { s0 += __shfl_xor_sync(~0u, s0, o); q0 += __shfl_xor_sync(~0u, q0, o); }
                if ((j & 3) == 0) {
                    const float d = s0 * (1.0f / DM);
                    const uint32_t ms = pack2(p0[0] + d, sqrt_apx(rbf(rbf(fmaxf(fmaf(-d, d, q0 * (1.0f / DM)), 0.f)) + 1e-5f)));
                    asm volatile("st.global.cg.u64 [%0], %1;" ::"l"(g_rstat + mb * 128 + (j & 4) * 16 + hg * 8 + (j >> 3)), "l"(tagw(ms, tag)) : "memory");
                    g_piv[mb * 128 + hg * 16 + ((j >> 2) & 8) + (j & 4) + ((j >> 3) & 3)] = __ushort_as_bfloat16((unsigned short)ms);
                }
                ulonglong2 v;
#pragma unroll 1
                for (int it = 0; it < SPIN_MAX; it++) {
                    v = ld_tag2(reinterpret_cast<const ulonglong2*>(g_rstat + mb * 128) + j);
                    if (__all_sync(~0u, tag_ok(v, tag))) break;
                    __nanosleep(100);
                }
                o[0] = __uint_as_float((uint32_t)v.x << 16); o[1] = rcp_apx(__uint_as_float((uint32_t)v.x & 0xffff0000u));
                o[2] = __uint_as_float((uint32_t)v.y << 16); o[3] = rcp_apx(__uint_as_float((uint32_t)v.y & 0xffff0000u));
                row = 2 * j;
            } else {
#pragma unroll
                for (int i = 0; i < 4; i++) {
                    const bool up = kg & 2;
                    const float ss = __shfl_xor_sync(~0u, up ? s[i] : s[i + 4], 16), qq = __shfl_xor_sync(~0u, up ? q[i] : q[i + 4], 16);
                    s[i] = (up ? s[i + 4] : s[i]) + ss; q[i] = (up ? q[i + 4] : q[i]) + qq; p0[i] = up ? p0[i + 4] : p0[i];
                }
#pragma unroll
                for (int i = 0; i < 2; i++) {
                    const bool up = kg & 1;
                    const float ss = __shfl_xor_sync(~0u, up ? s[i] : s[i + 2], 8), qq = __shfl_xor_sync(~0u, up ? q[i] : q[i + 2], 8);
                    s[i] = (up ? s[i + 2] : s[i]) + ss; q[i] = (up ? q[i + 2] : q[i]) + qq; p0[i] = up ? p0[i + 2] : p0[i];
                }
                uint4* gp = g_halo + 86016 + mb * 512 + j;
                const float d0 = s[0] * (1.0f / 80.0f), d1 = s[1] * (1.0f / 80.0f);
                asm volatile("st.relaxed.gpu.global.v4.f32 [%0], {%1,%2,%3,%4};" ::"l"(gp + hg * 64), "f"(p0[0] + d0), "f"(fmaxf(fmaf(-d0, s[0], q[0]), 0.f)), "f"(p0[1] + d1), "f"(fmaxf(fmaf(-d1, s[1], q[1]), 0.f)) : "memory");
                __nanosleep(ST_SLEEP0);
                uint32_t pw[8][4], todo = 0xff;
#pragma unroll 1
                for (int it = 0; it < SPIN_MAX; it++) {
#pragma unroll
                    for (int k = 0; k < 8; k++)
                        if (todo >> k & 1) asm volatile("ld.relaxed.gpu.global.v4.u32 {%0,%1,%2,%3}, [%4];" : "=r"(pw[k][0]), "=r"(pw[k][1]), "=r"(pw[k][2]), "=r"(pw[k][3]) : "l"(gp + k * 64) : "memory");
#pragma unroll
                    for (int k = 0; k < 8; k++)
                        if (__all_sync(~0u, pw[k][0] != ~0u && pw[k][1] != ~0u && pw[k][2] != ~0u && pw[k][3] != ~0u)) todo &= ~(1u << k);
                    if (!todo) break;
                    __nanosleep(ST_SLEEP);
                }
#pragma unroll
                for (int r = 0; r < 2; r++) {
                    float mean = 0.f, m2 = 0.f;
#pragma unroll
                    for (int k = 0; k < 8; k++) mean += __uint_as_float(pw[k][2 * r]);
                    mean *= 0.125f;
#pragma unroll
                    for (int k = 0; k < 8; k++) {
                        const float dm = __uint_as_float(pw[k][2 * r]) - mean;
                        m2 += fmaf(80.0f * dm, dm, __uint_as_float(pw[k][2 * r + 1]));
                    }
                    o[2 * r] = rbf(mean);
                    o[2 * r + 1] = rcp_apx(rbf(sqrt_apx(rbf(rbf(m2 * (1.0f / DM)) + 1e-5f))));
                }
                row = (j >> 5) * 64 + (j & 7) * 8 + ((j >> 3) & 3) * 2;
                if (hg == 0) *reinterpret_cast<uint32_t*>(g_piv + SEQ + mb * 128 + 2 * (row & 60) + 4 * (row >> 6) + (row & 3)) = __byte_perm(__float_as_uint(o[0]), __float_as_uint(o[2]), 0x7632);
            }
#pragma unroll
            for (int r = 0; r < 2; r++)
                *reinterpret_cast<uint4*>(stg + A1_SM_XA + (row + r) * 16) = make_uint4(__byte_perm(__float_as_uint(-o[2 * r]), 0, 0x3232), __float_as_uint(-o[2 * r]) >> 16, 0u, 0u);
            *reinterpret_cast<float4*>(rst + row + (row >> 6) * 8) = make_float4(o[0], o[1], o[2], o[3]);
            fence_async_smem();
            TSTAMP1T(7, 320); CSA(1);
            if (tid == 320) DBGC(44);
            __syncwarp();
            if ((tid & 31) == 0) mbar_arrive(bar_stat);
        }
        CSA(4); CSA_END;
        if (tid == 320) DBGCAL(0);
        __syncwarp();
        if (w == WOT) {
            mbar_wait(bar_done, 0);
            if (one) {
                bulk_load(sbase, wo + (hg * 8 + 6) * WOB, 2 * WOB, bar_wo);
                bulk_load(sbase + A1_SM_W0 + 2 * WOB, wo + (hg * 8 + 2) * WOB, WOB, bar_wo);
            }
            __syncwarp();
        }
#define FWA 11
#define FWB 10
        if (w == FWA || w == FWB) {
            const int cw = w == FWB;
            const uint32_t* fl = reinterpret_cast<const uint32_t*>(rsum + 2 * SEQ) + (((layer * 16 + mb) * 2 + cw) * 8 + (tid & 7)) * FSTR;
            const unsigned char* src = reinterpret_cast<const unsigned char*>(of) + mb * 163840 + cw * 10240 + (tid & 7) * 20480;
            const uint32_t sl = sbase + (cw ? A1_SM_A1 : A1_SM_A0);
            mbar_wait(cw ? bar_done : bar_kvf, 0);
            if (one) {
                mbar_expect_tx(bar_f2 + 64 * cw + 64, 10240);
                tma_load_3d(sl + 51200, &tmR, layer ? 0 : hg * 80, layer ? hg * 80 : mb * 64, layer ? mb * 2 + cw : cw, bar_f2 + 64 * cw + 64);
            }
            __syncwarp();
            uint32_t pend = 0xffu & ~(1u << hg), v = 0;
            const uint32_t bo = wo_off((tid & 7) + ((tid & 7) < hg)) >> 4, lt = (1u << (tid & 31)) - 1;
#pragma unroll 1
            for (int it = 0; pend && it < 2 * SPIN_MAX; it++) {
                if (v != 4 && (pend >> (tid & 31) & 1)) asm volatile(A1_FLD " %0, [%1];" : "=r"(v) : "l"(fl) : "memory");
                uint32_t fr;
                asm volatile("{\n.reg .pred p;\nmbarrier.test_wait.parity.shared::cta.b64 p, [%1], 0;\nselp.b32 %0, 1, 0, p;\n}" : "=r"(fr) : "r"(bar_e2 + 16 * cw + (tid & 1) * 8) : "memory");
                fr = __ballot_sync(~0u, fr);
                uint32_t m = __ballot_sync(~0u, v == 4 || it >= A1_FSPIN) & pend;
                const int q = 8 - __popc(pend) + __popc(m & lt);
                m &= __ballot_sync(~0u, q < ((fr & 2) ? 8 : (fr & 1) ? 7 : 5));
                pend ^= m;
                if (m >> (tid & 31) & 1) DBGC(12 + cw * 8 + (tid & 7));
                if (!m) __nanosleep(A1_FSLEEP);
                else asm volatile("fence.proxy.async.global;" ::: "memory");
                if (m >> (tid & 31) & 1) {
                    bulk_load(q == 7 && !cw ? sbase + A1_SM_W0 : sl + (q < 6 ? q : q - 6) * 10240, src, 10240, bar_f2 + 64 * cw + 8 * q);
                    asm volatile("st.shared.u32 [%0], %1;" ::"r"(que + 32 * cw + 4 * q), "r"(bo) : "memory");
                    mbar_expect_tx(bar_f2 + 64 * cw + 8 * q, 10240);
                    DBGC(44 + cw * 8 + q);
                }
                __syncwarp();
            }
        }
    } else if (tile < 128) {
        SPAN(1 + 4 * layer, 0);
        constexpr int on = 1;
        float acc[120];
        const int lane = tid & 31, warp = w & 7, g = lane >> 2, t = lane & 3;
        if (on) {
            SPAN(1 + 4 * layer, 1);
            TSTAMP1(0);
            if (threadIdx.x == 0) { GSTAMP(g_tim1, 15); }
            TSTAMP3(0);
            if (tid == 0) TSTAMP2(0);
            TSTAMP4(0);
            if (tid == 0) DBGC(60);
            if (layer == 0) a1_mainloop<0>(acc, sbase, bars, wg, tile); else a1_mainloop<1>(acc, sbase, bars, wg, tile);
            uint32_t ok;
            asm volatile("{\n.reg .pred p;\nmbarrier.test_wait.parity.shared::cta.b64 p, [%1], 0;\nselp.b32 %0, 1, 0, p;\n}" : "=r"(ok) : "r"(bar_stat) : "memory");
            if (tid == 128 && !ok) mbar_arrive(bars + 160);
            __syncwarp();
            mbar_wait(bar_stat, 0);
            wgmma_fence();
            wgmma_n240<0, 0>(acc, make_desc(sbase + A1_SM_XA + wg * 1024, 0, 128, 0), make_desc(sbase + A1_SM_XB, 0, 128, 0), 1);
            wgmma_commit();
            if (tid == 128 && ok) mbar_arrive(bars + 160);
            mbar_wait(bars + 8 * (A1_NST + 3), 1);
        }
        const float2* rw = rst + 16 * warp + 8 * wg;
        const float rb0 = rw[g + 8].y, ra = rw[g].y * 0.22360679774997896f, rb = rb0 * 0.22360679774997896f;
        wgmma_wait<0>();
        if ((tid & 127) == 0) mbar_arrive(bar_done);
        TSTAMP1(2); CSA(1);
        TSTAMP1T(13, 224);
        if ((tid & 127) == 0) DBGC(62 - wg);
        uint32_t f[2][30];
#pragma unroll
        for (int j = 10; j < 30; j++) f[1][j] = pack2(acc[4 * j + 2], acc[4 * j + 3]);
        if ((warp & 3) == 3) {
            uint4* hout = g_halo + (((layer * 16 + mb) * 8 + hg) * 2 + wg) * 168;
#pragma unroll
            for (int j = 0; j < 20; j += 4)
                asm volatile("st.relaxed.gpu.global.v4.u32 [%0], {%1,%2,%3,%4};" ::"l"(hout + 8 * j + lane), "r"(f[1][10 + j]), "r"(f[1][11 + j]), "r"(f[1][12 + j]), "r"(f[1][13 + j]) : "memory");
            if (t == 0) asm volatile("st.relaxed.gpu.global.f32 [%0], %1;" ::"l"(reinterpret_cast<float*>(hout + 160) + g), "f"(rb0) : "memory");
        }
        TSTAMP1T(12, 224);
        const uint32_t kvw = sbase + A1_SM_KV + (16 * warp + 8 * wg) * A1_KVP;
        const uint32_t mrow = kvw + (lane & 7) * A1_KVP + (lane >> 3) * 16;
#pragma unroll
        for (int j = 0; j < 20; j += 4) stsm_x4(mrow + 16 * A1_KVP + 16 * j, f[1][10 + j], f[1][11 + j], f[1][12 + j], f[1][13 + j]);
        __syncwarp();
        if (lane == 0 && (warp & 3) != 3) mbar_arrive(bar_kv + 8 * (warp + 1));
#pragma unroll
        for (int j = 0; j < 30; j++) f[0][j] = pack2(acc[4 * j], acc[4 * j + 1]);
        stsm_x4(mrow + 8 * A1_KVP + 160, f[0][20], f[0][21], f[0][22], f[0][23]);
        stsm_x4(mrow + 8 * A1_KVP + 224, f[0][24], f[0][25], f[0][26], f[0][27]);
        asm volatile("stmatrix.sync.aligned.m8n8.x2.shared.b16 [%0], {%1,%2};" ::"r"(mrow + 8 * A1_KVP + 288), "r"(f[0][28]), "r"(f[0][29]) : "memory");
#pragma unroll
        for (int j = 0; j < 10; j++) f[1][j] = pack2(acc[4 * j + 2], acc[4 * j + 3]);
        __syncwarp();
        uint32_t vb[10][2], vp[12], kp[12];
#pragma unroll
        for (int j = 0; j < 10; j += 2) ldsm_x4_t(&vb[j][0], kvw + (8 + (lane & 15)) * A1_KVP + 160 + (lane >> 4) * 16 + 16 * j);
        const bool up0 = 2 * t > g, up1 = 2 * t + 1 > g, edge = (mb | (warp & 3)) == 0;
        float rk[4];
        auto above = [&]() {
            mbar_wait(bar_kv + 8 * warp, 0);
#pragma unroll
            for (int j = 0; j < 12; j += 4) ldsm_x4(&kp[j], mrow + 16 * j);
            rk[0] = rw[2 * t - (up0 ? 8 : 0)].y; rk[1] = rw[2 * t + 1 - (up1 ? 8 : 0)].y;
#pragma unroll
            for (int j = 0; j < 12; j += 4) ldsm_x4_t(&vp[j], mrow + 160 + 16 * j - (j == 8 ? (lane & 16) * 2 : 0));
            __syncwarp();
            if (lane == 0) mbar_arrive(bar_kvf);
        };
        auto halo = [&]() {
            if (lane == 0) mbar_arrive(bar_kvf);
            const uint4* hin = g_halo + (((layer * 16 + mb - 1) * 8 + hg) * 2 + wg) * 168;
            uint32_t hv[22] = {};
            rk[0] = rw[2 * t].y; rk[1] = rw[2 * t + 1].y;
            if (mb > 0) {
#pragma unroll 1
                for (int it = 0; it < SPIN_MAX; it++) {
#pragma unroll
                    for (int k = 0; k < 20; k += 4)
                        asm volatile("ld.relaxed.gpu.global.v4.u32 {%0,%1,%2,%3}, [%4];" : "=r"(hv[k]), "=r"(hv[k + 1]), "=r"(hv[k + 2]), "=r"(hv[k + 3]) : "l"(hin + 8 * k + lane) : "memory");
                    asm volatile("ld.relaxed.gpu.global.v2.u32 {%0,%1}, [%2];" : "=r"(hv[20]), "=r"(hv[21]) : "l"(reinterpret_cast<const uint2*>(hin + 160) + t) : "memory");
                    uint32_t m = max(hv[20], hv[21]);
#pragma unroll
                    for (int k = 0; k < 20; k += 2) m = __vimax3_u32(m, hv[k], hv[k + 1]);
                    if (!__any_sync(~0u, m == ~0u)) break;
                }
            }
            if (lane == 0) DBGC(52 - 16 * wg);
#pragma unroll
            for (int j = 0; j < 10; j++) {
                kp[j] = hv[j];
                asm volatile("movmatrix.sync.aligned.m8n8.trans.b16 %0, %1;" : "=r"(vp[j]) : "r"(hv[10 + j]));
            }
            if (up0) rk[0] = __uint_as_float(hv[20]);
            if (up1) rk[1] = __uint_as_float(hv[21]);
        };
        rk[2] = rw[2 * t + (up0 ? 0 : 8)].y; rk[3] = rw[2 * t + 1 + (up1 ? 0 : 8)].y;
        uint32_t qs[4][2];
#pragma unroll
        for (int h = 0; h < 4; h++) {
            qs[h][0] = (t >> 1) == (h & 1) ? f[0][5 * (h >> 1) + 2] : 0u; qs[h][1] = (t >> 1) == (h & 1) ? f[1][5 * (h >> 1) + 2] : 0u;
            asm volatile("" : "+r"(qs[h][0]), "+r"(qs[h][1]));
        }
#pragma unroll
        for (int j = 0; j < 10; j++) asm volatile("" : "+r"(f[0][j]), "+r"(f[1][j]), "+r"(f[0][10 + j]));
        if (warp & 3) above(); else if (wg) halo();
        TSTAMP1T(10, 64); CSA(2);
        if (warp && !wg) mbar_wait(bars + 416 + 8 * warp, 0);
        CSA(3);
        float sc[4][3][4];
#pragma unroll
        for (int h = 0; h < 4; h++) {
            const int jb = 5 * (h >> 1) + 3 * (h & 1), js = 5 * (h >> 1) + 2;
#pragma unroll
            for (int nt = 1; nt < 3; nt++) {
#pragma unroll
                for (int e = 0; e < 4; e++) sc[h][nt][e] = 0.f;
                mma_bf16(sc[h][nt], f[0][jb], f[1][jb], f[0][jb + 1], f[1][jb + 1], f[nt - 1][10 + jb], f[nt - 1][11 + jb]);
                mma_bf16_k8(sc[h][nt], qs[h][0], qs[h][1], f[nt - 1][10 + js]);
            }
        }
        if (warp == 0) halo();
        TSTAMP1(8); CSA(4);
#pragma unroll
        for (int h = 0; h < 4; h++) {
            const int jb = 5 * (h >> 1) + 3 * (h & 1), js = 5 * (h >> 1) + 2;
#pragma unroll
            for (int e = 0; e < 4; e++) sc[h][0][e] = 0.f;
            mma_bf16(sc[h][0], f[0][jb], f[1][jb], f[0][jb + 1], f[1][jb + 1], kp[jb], kp[jb + 1]);
            mma_bf16_k8(sc[h][0], qs[h][0], qs[h][1], kp[js]);
        }
        TSTAMP1T(3, 64);
        float p[4][4], sum[4][2];
        uint32_t lg[4][2], mx[4];
        const float rl[4] = {rk[0] * ra, rk[1] * ra, rk[2] * rb, rk[3] * rb};
        auto max2 = [](uint32_t a, uint32_t b) { uint32_t r; asm("max.bf16x2 %0, %1, %2;" : "=r"(r) : "r"(a), "r"(b)); return r; };
#pragma unroll
        for (int h = 0; h < 4; h++) {
            lg[h][0] = pack2((up0 ? sc[h][0][0] : sc[h][1][0]) * rl[0], (up0 ? sc[h][1][2] : sc[h][2][2]) * rl[2]);
            lg[h][1] = pack2((up1 ? sc[h][0][1] : sc[h][1][1]) * rl[1], (up1 ? sc[h][1][3] : sc[h][2][3]) * rl[3]);
            if (edge) {
                if (up0) lg[h][0] = __byte_perm(lg[h][0], 0xce6eu, 0x3254);
                if (up1) lg[h][1] = __byte_perm(lg[h][1], 0xce6eu, 0x3254);
            }
            mx[h] = max2(lg[h][0], lg[h][1]);
        }
#pragma unroll
        for (int o = 1; o <= 2; o <<= 1)
#pragma unroll
            for (int h = 0; h < 4; h++) mx[h] = max2(mx[h], __shfl_xor_sync(~0u, mx[h], o));
#pragma unroll
        for (int h = 0; h < 4; h++)
#pragma unroll
            for (int r = 0; r < 2; r++) {
                const float m = __uint_as_float(r ? mx[h] & 0xffff0000u : mx[h] << 16);
#pragma unroll
                for (int e = 0; e < 2; e++)
                    asm("ex2.approx.ftz.f32 %0, %1;" : "=f"(p[h][2 * r + e]) : "f"((__uint_as_float(r ? lg[h][e] & 0xffff0000u : lg[h][e] << 16) - m) * 1.4426950408889634f));
                sum[h][r] = p[h][2 * r] + p[h][2 * r + 1];
            }
#pragma unroll
        for (int o = 1; o <= 2; o <<= 1)
#pragma unroll
            for (int h = 0; h < 4; h++)
#pragma unroll
                for (int r = 0; r < 2; r++) sum[h][r] += __shfl_xor_sync(~0u, sum[h][r], o);
        TSTAMP1T(5, 64); CSA(5);
        const uint32_t mu = (up0 ? 0xffffu : 0u) | (up1 ? 0xffff0000u : 0u);
        uint32_t ob[10][2];
#pragma unroll
        for (int P = 0; P < 2; P++) {
            float os[2][4];
#pragma unroll
            for (int e = 0; e < 2; e++) {
                const int h = 2 * P + e;
                const float i0 = rcp_apx(sum[h][0]), i1 = rcp_apx(sum[h][1]);
                const uint32_t w0 = pack2(p[h][0] * rk[0] * i0, p[h][1] * rk[1] * i0), w1 = pack2(p[h][2] * rk[2] * i1, p[h][3] * rk[3] * i1);
#pragma unroll
                for (int dt = 0; dt < 3; dt++) {
                    const int j = 5 * P + (dt < 2 ? 3 * e + dt : 2);
                    float o[4] = {0.f, 0.f, 0.f, 0.f};
                    mma_bf16(o, w0 & ~mu, w1 & mu, 0u, w1 & ~mu, vb[j][0], vb[j][1]);
                    mma_bf16_k8(o, w0 & mu, 0u, vp[j]);
                    if (dt < 2) { ob[j][0] = pack2(o[0], o[1]); ob[j][1] = pack2(o[2], o[3]); }
                    else { os[e][0] = o[0]; os[e][1] = o[1]; os[e][2] = o[2]; os[e][3] = o[3]; }
                }
            }
#pragma unroll
            for (int k = 0; k < 4; k++) os[0][k] = t < 2 ? os[0][k] : os[1][k];
            ob[5 * P + 2][0] = pack2(os[0][0], os[0][1]); ob[5 * P + 2][1] = pack2(os[0][2], os[0][3]);
        }
        const uint32_t sl = sbase + (wg ? A1_SM_A1 : A1_SM_A0);
        const uint32_t o0 = (warp & 3) * 2048 + g * 64 + ((t ^ (g >> 1)) << 4), o1 = 8192 + (warp & 3) * 512 + g * 32 + ((t ^ ((g >> 2) << 1)) << 3);
        CSA(15);
        mbar_wait(bar_done, 0);
        if (wg == 0) mbar_wait(bar_kvf, 0);
#pragma unroll
        for (int h = 0; h < 2; h++) {
            asm volatile("st.shared.v4.u32 [%0], {%1,%2,%3,%4};" ::"r"(sl + o0 + h * 1024), "r"(ob[0][h]), "r"(ob[1][h]), "r"(ob[2][h]), "r"(ob[3][h]) : "memory");
            asm volatile("st.shared.v4.u32 [%0], {%1,%2,%3,%4};" ::"r"(sl + o0 + h * 1024 + 512), "r"(ob[4][h]), "r"(ob[5][h]), "r"(ob[6][h]), "r"(ob[7][h]) : "memory");
            asm volatile("st.shared.v2.u32 [%0], {%1,%2};" ::"r"(sl + o1 + h * 256), "r"(ob[8][h]), "r"(ob[9][h]) : "memory");
        }
        if (wg && lane == 0) mbar_arrive(bars + 384 + 8 * warp);
        fence_async_smem();
        __syncwarp();
        TSTAMP1T(4, 64); CSA(6);
        TSTAMP1(1);
        TSTAMP2(1);
        const unsigned char* ot = reinterpret_cast<const unsigned char*>(of) + mb * 163840 + wg * 10240;
        if (lane == 0) {
            asm volatile("cp.async.bulk.global.shared::cta.bulk_group [%0], [%1], 2048;" ::"l"(ot + hg * 20480 + (warp & 3) * 2048), "r"(sl + (warp & 3) * 2048) : "memory");
            asm volatile("cp.async.bulk.global.shared::cta.bulk_group [%0], [%1], 512;" ::"l"(ot + hg * 20480 + 8192 + (warp & 3) * 512), "r"(sl + 8192 + (warp & 3) * 512) : "memory");
            asm volatile("cp.async.bulk.commit_group;" ::: "memory");
            if (wg == 0) mbar_arrive(bar_pv);
            asm volatile("cp.async.bulk.wait_group 0;" ::: "memory");
            asm volatile(A1_FRED " [%0], 1;" ::"l"(reinterpret_cast<uint32_t*>(rsum + 2 * SEQ) + (((layer * 16 + mb) * 2 + wg) * 8 + hg) * FSTR) : "memory");
            DBGC(4 + warp);
        }
        TSTAMP4(11); CSA(7);
        float ac2[40];
        const uint64_t db0 = make_desc(sbase, 1024, 256, 3), db1 = make_desc(sbase + 10240, 512, 256, 3), da0 = make_desc(sl, 16, 1024, 2), da1 = make_desc(sl + 8192, 16, 256, 3);
        const uint32_t o7 = wg ? 640 : (A1_SM_W0 - A1_SM_A0) >> 4;
        const uint32_t trow = ((lane & 7) + 8 * (lane >> 4)) * 128 + (((2 * (warp & 3) + ((lane >> 3) & 1)) ^ (lane & 7)) << 4);
        uint32_t xr[10][2];
        mbar_wait(bar_f2 + 64 * wg + 64, 0);
        if (layer == 0) {
#pragma unroll
            for (int j = 0; j < 10; j += 2) ldsm_x4(&xr[j][0], sl + 51200 + (16 * (warp & 3) + (lane & 15)) * 160 + (lane >> 4) * 16 + 16 * j);
        } else {
#pragma unroll
            for (int j = 0; j < 10; j += 2) ldsm_x4_t(&xr[j][0], sl + 51200 + trow + 1024 * j);
        }
        const uint32_t ri = __shfl_sync(~0u, layer * SEQ + (wg * 2 + ((g >> 1) & 1)) * 512 + (mb * 16 + 4 * (warp & 3) + (g >> 2)) * 2 + (g & 1), lane);
        mbar_wait(bar_wo, 0);
        if (wg) mbar_wait(bar_pv, 0);
        if (wg) asm volatile("bar.sync 2, 128;" ::: "memory"); else asm volatile("bar.sync 1, 128;" ::: "memory");
        TSTAMP2(2); CSA(8);
#pragma unroll
        for (int q = 0; q < 8; q++) {
            uint32_t bo = wo_off(0) >> 4;
            if (q) {
                mbar_wait(bar_f2 + 64 * wg + 8 * q, 0);
                asm volatile("ld.shared.u32 %0, [%1];" : "=r"(bo) : "r"(que + 32 * wg + 4 * q) : "memory");
                bo = __shfl_sync(~0u, bo, 0);
                TSTAMP4(q);
                if (q % 3 == 1) CSA(9 + q / 3);
                if (q == 1 && (tid & 127) == 0) DBGC(29 + 8 * wg);
            }
            wgmma_fence();
#pragma unroll
            for (int j = 0; j < 5; j++) wgmma_n80(ac2, (j < 4 ? da0 : da1) + (q == 7 ? o7 : 0u) + (uint64_t)((q < 6 ? q * 640 : 0) + (j & 2) * 16 + (j & 1) * 2), (j < 4 ? db0 : db1) + bo + (uint64_t)((j & 2) * 160 + (j & 1) * 32), j || q);
            wgmma_commit();
            if (q == 0) {
                wgmma_wait<0>();
                if ((tid & 127) == 0) { mbar_arrive(bar_e2 + 16 * wg); mbar_arrive(bar_e2 + 8); }
            }
            if (q == 2 && wg) {
                wgmma_wait<1>();
                if (tid == 128) mbar_arrive(bar_e2 + 24);
            }
        }
        if ((tid & 127) == 0) DBGC(28 + wg * 8 + 7);
        TSTAMP2(3);
        wgmma_wait<0>();
        TSTAMP2(4); CSA(12);
        if (__any_sync(~0u, ac2[0] != ac2[0] || ac2[2] != ac2[2])) {
#pragma unroll
            for (int i = 0; i < 40; i++) ac2[i] = 0.f;
            uint32_t a[20], an[20];
            auto lda = [&](uint32_t (&r)[20], int h) {
#pragma unroll
                for (int u = 0; u < 4; u++)
                    asm volatile("ld.relaxed.gpu.global.v4.u32 {%0,%1,%2,%3}, [%4];" : "=r"(r[4 * u]), "=r"(r[4 * u + 1]), "=r"(r[4 * u + 2]), "=r"(r[4 * u + 3]) : "l"(ot + h * 20480 + o0 + u * 512) : "memory");
#pragma unroll
                for (int u = 0; u < 2; u++)
                    asm volatile("ld.relaxed.gpu.global.v2.u32 {%0,%1}, [%2];" : "=r"(r[16 + 2 * u]), "=r"(r[17 + 2 * u]) : "l"(ot + h * 20480 + o1 + u * 256) : "memory");
            };
            lda(an, 0);
#pragma unroll 5
            for (int k = lane; k < WOB / 16; k += 32)
                reinterpret_cast<uint4*>(stg + (sl - sbase))[k] = __ldcg(reinterpret_cast<const uint4*>(wo + hg * 8 * WOB) + k);
            __syncwarp();
#pragma unroll 1
            for (int h = 0; h < 8; h++) {
#pragma unroll 1
                for (int it = 0; it < SPIN_MAX; it++) {
                    uint32_t m = 0;
#pragma unroll
                    for (int k = 0; k < 20; k += 2) m = __vimax3_u32(m, an[k], an[k + 1]);
                    if (!__any_sync(~0u, m == ~0u)) break;
                    lda(an, h);
                }
#pragma unroll
                for (int k = 0; k < 20; k++) a[k] = an[k];
                lda(an, min(h + 1, 7));
                const uint32_t bp = h == hg ? sl : sbase + wo_off(h + (h < hg));
                const int r0 = 8 * ((lane & 7) >> 1) + 2 * (lane >> 3) + (lane & 1), r2 = 4 * ((lane & 7) >> 1) + 2 * ((lane >> 3) & 1) + (lane & 1);
#pragma unroll
                for (int n = 0; n < 10; n++) {
                    uint32_t b[12];
                    ldsm_x4_t(b, bp + (n >> 1) * 1024 + r0 * 32 + (((n ^ (r0 >> 2)) & 1) << 4));
                    ldsm_x4_t(b + 4, bp + 5120 + (n >> 1) * 1024 + r0 * 32 + (((n ^ (r0 >> 2)) & 1) << 4));
                    ldsm_x4_t(b + 8, bp + 10240 + (n >> 1) * 512 + r2 * 32 + (((n ^ (r2 >> 2)) & 1) << 4));
                    mma_bf16(ac2 + 4 * n, a[0], a[8], a[1], a[9], b[0], b[1]); mma_bf16(ac2 + 4 * n, a[2], a[10], a[3], a[11], b[2], b[3]);
                    mma_bf16(ac2 + 4 * n, a[4], a[12], a[5], a[13], b[4], b[5]); mma_bf16(ac2 + 4 * n, a[6], a[14], a[7], a[15], b[6], b[7]);
                    mma_bf16(ac2 + 4 * n, a[16], a[18], a[17], a[19], b[8], b[9]);
                }
            }
        }
#pragma unroll
        for (int j = 0; j < 10; j++)
#pragma unroll
            for (int hh = 0; hh < 2; hh++) {
                const uint32_t a = pack2(ac2[4 * j + 2 * hh], ac2[4 * j + 2 * hh + 1]);
                const __nv_bfloat162 r = __hadd2_rn(*reinterpret_cast<const __nv_bfloat162*>(&xr[j][hh]), *reinterpret_cast<const __nv_bfloat162*>(&a));
                xr[j][hh] = *reinterpret_cast<const uint32_t*>(&r);
            }
        const uint32_t so = sl + 30720;
#pragma unroll
        for (int j = 0; j < 10; j += 2) stsm_x4_t(so + trow + 1024 * j, xr[j][0], xr[j][1], xr[j + 1][0], xr[j + 1][1]);
        if (wg) asm volatile("bar.sync 2, 128;" ::: "memory"); else asm volatile("bar.sync 1, 128;" ::: "memory");
        TSTAMP2(5); CSA(13);
        if ((tid & 127) == 0) {
            fence_async_smem();
            asm volatile("cp.async.bulk.tensor.2d.global.shared::cta.bulk_group [%0, {%1, %2}], [%3];" ::"l"(&tmX1), "r"(mb * 128 + 64 * wg), "r"(hg * 80), "r"(so) : "memory");
            asm volatile("cp.async.bulk.commit_group;" ::: "memory");
        }
        __syncwarp();
        const float p0 = *(volatile const float*)&rw[g].x, p1 = *(volatile const float*)&rw[g + 8].x;
        float s[3][4] = {};
        const uint32_t pp[2] = {__byte_perm(__float_as_uint(p0), 0, 0x3232), __byte_perm(__float_as_uint(p1), 0, 0x3232)};
#pragma unroll
        for (int j = 0; j < 10; j += 2) {
            const uint32_t d0 = sub2(xr[j][0], pp[0]), d1 = sub2(xr[j][1], pp[1]), d2 = sub2(xr[j + 1][0], pp[0]), d3 = sub2(xr[j + 1][1], pp[1]);
            mma_bf16(s[0], xr[j][0], xr[j][1], xr[j + 1][0], xr[j + 1][1], 0x3f803f80u, 0x3f803f80u);
            mma_bf16(s[1], d0, d1, d2, d3, d0, d2);
            mma_bf16(s[2], d0, d1, d2, d3, d1, d3);
        }
        if (t == (g >> 1)) {
            float2* rp = rsum + ri;
            asm volatile("red.relaxed.gpu.global.add.v2.f32 [%0], {%1, %2};" ::"l"(rp), "f"(fmaf(-80.f, p0, s[0][0])), "f"((g & 1) ? s[1][1] : s[1][0]) : "memory");
            asm volatile("red.relaxed.gpu.global.add.v2.f32 [%0], {%1, %2};" ::"l"(rp + 4), "f"(fmaf(-80.f, p1, s[0][2])), "f"((g & 1) ? s[2][3] : s[2][2]) : "memory");
        }
        asm volatile("cp.async.bulk.wait_group.read 0;" ::: "memory");
        TSTAMP2(6); CSA(14); CSA_END;
        if (tid == 0) DBGC(63);
        if (tid == 128) DBGC(28);
        if (tid == 0) DBGCAL(2);
        GSTAMP(g_tim1, 14);
        SPAN(1 + 4 * layer, 3);
    }
#undef layer
}

static int h_nsm;
static void* h_sym[11];
static TileTab h_tab[2];
static CUtensorMap h_tmX0, h_tmX1, h_tmR0, h_tmR1, h_tmX1st, h_tmOut;
static KgMaps h_tmW;
typedef CUresult (*PFN_encodeTiled)(CUtensorMap*, CUtensorMapDataType, cuuint32_t, void*, const cuuint64_t*, const cuuint64_t*,
                                    const cuuint32_t*, const cuuint32_t*, CUtensorMapInterleave, CUtensorMapSwizzle,
                                    CUtensorMapL2promotion, CUtensorMapFloatOOBfill);
static void make_tmap(CUtensorMap* tm, const void* ptr, uint64_t cols, uint64_t rows, uint32_t bc, uint32_t br, CUtensorMapSwizzle sw, uint64_t pitch = 0, uint64_t hi = 0, uint32_t bh = 2) {
    static PFN_encodeTiled fn = nullptr;
    if (!fn) {
        void* p = nullptr; cudaDriverEntryPointQueryResult qr;
        cudaGetDriverEntryPoint("cuTensorMapEncodeTiled", &p, cudaEnableDefault, &qr);
        fn = (PFN_encodeTiled)p;
    }
    if (br == 0) {
        cuuint64_t dims[5] = {16, 2, rows / 8, 4, cols / 16}; cuuint64_t strides[4] = {cols * 2, cols * 16, cols * 4, 32};
        cuuint32_t box[5] = {16, 2, bc, 4, 5}; cuuint32_t es[5] = {1, 1, 1, 1, 1};
        fn(tm, CU_TENSOR_MAP_DATA_TYPE_BFLOAT16, 5, const_cast<void*>(ptr), dims, strides, box, es, CU_TENSOR_MAP_INTERLEAVE_NONE, sw,
           CU_TENSOR_MAP_L2_PROMOTION_L2_128B, CU_TENSOR_MAP_FLOAT_OOB_FILL_NONE);
        return;
    }
    if (hi == 16) {
        cuuint64_t dims[4] = {16, 32, 120, 20}; cuuint64_t strides[3] = {3840, 32, 32 * 3840};
        cuuint32_t box[4] = {16, 32, 5, 2}; cuuint32_t es[4] = {1, 1, 1, 1};
        fn(tm, CU_TENSOR_MAP_DATA_TYPE_BFLOAT16, 4, const_cast<void*>(ptr), dims, strides, box, es, CU_TENSOR_MAP_INTERLEAVE_NONE, sw,
           CU_TENSOR_MAP_L2_PROMOTION_L2_128B, CU_TENSOR_MAP_FLOAT_OOB_FILL_NONE);
        return;
    }
    if (bh == 0) {
        cuuint64_t dims[5] = {64, 64, 2, 16, 10}; cuuint64_t strides[4] = {pitch * 2, hi * 2, cols * 2, rows * 2};
        cuuint32_t box[5] = {64, 64, 2, 1, 1}; cuuint32_t es[5] = {1, 1, 1, 1, 1};
        fn(tm, CU_TENSOR_MAP_DATA_TYPE_BFLOAT16, 5, const_cast<void*>(ptr), dims, strides, box, es, CU_TENSOR_MAP_INTERLEAVE_NONE, sw,
           CU_TENSOR_MAP_L2_PROMOTION_L2_128B, CU_TENSOR_MAP_FLOAT_OOB_FILL_NONE);
        return;
    }
    if (hi) {
        cuuint64_t dims[3] = {cols, rows, hi == 64 ? 32u : 2u}; cuuint64_t strides[2] = {pitch * 2, hi * 2};
        cuuint32_t box[3] = {bc, br, bh}; cuuint32_t es[3] = {1, 1, 1};
        fn(tm, CU_TENSOR_MAP_DATA_TYPE_BFLOAT16, 3, const_cast<void*>(ptr), dims, strides, box, es, CU_TENSOR_MAP_INTERLEAVE_NONE, sw,
           CU_TENSOR_MAP_L2_PROMOTION_L2_128B, CU_TENSOR_MAP_FLOAT_OOB_FILL_NONE);
        return;
    }
    cuuint64_t dims[2] = {cols, rows}; cuuint64_t strides[1] = {(pitch ? pitch : cols) * 2};
    cuuint32_t box[2] = {bc, br}; cuuint32_t es[2] = {1, 1};
    fn(tm, CU_TENSOR_MAP_DATA_TYPE_BFLOAT16, 2, const_cast<void*>(ptr), dims, strides, box, es, CU_TENSOR_MAP_INTERLEAVE_NONE, sw,
       CU_TENSOR_MAP_L2_PROMOTION_L2_128B, CU_TENSOR_MAP_FLOAT_OOB_FILL_NONE);
}
template <typename... Args>
static void launch_pdl(void (*kern)(Args...), int grid, int block, int smem, Args... args) {
    cudaLaunchConfig_t cfg = {};
    cfg.gridDim = dim3(grid); cfg.blockDim = dim3(block); cfg.dynamicSmemBytes = smem; cfg.stream = cudaStreamPerThread;
    cudaLaunchAttribute at[1];
    at[0].id = cudaLaunchAttributeProgrammaticStreamSerialization; at[0].val.programmaticStreamSerializationAllowed = 1;
    cfg.attrs = at; cfg.numAttrs = 1;
    cudaLaunchKernelEx(&cfg, kern, args...);
}
static void launch_stage(int k, void* const* d_in, void* d_out) {
    const Par par = {k > 1 ? nullptr : (const bf16*)d_in[4], (const bf16*)d_in[5], (const bf16*)d_in[6], (const bf16*)d_in[7], (const bf16*)d_in[8], (const bf16*)d_in[9], k > 1, 0, (const bf16*)d_in[0],
                     (uint4*)h_sym[4], (uint4*)h_sym[2], (uint4*)h_sym[6], (uint4*)h_sym[3], (uint4*)h_sym[0], (float*)h_sym[5], (uint4*)h_sym[1], (const bf16*)d_in[1], (const bf16*)d_in[2]};
    auto a1 = h_nsm == 132 ? a1_kernel<true> : a1_kernel<false>;
    switch (k) {
        case 1: a1<<<h_nsm, A1_THREADS, A1_SMEM, cudaStreamPerThread>>>(par, h_tmX0, h_tmR0, h_tmX1st, h_tmW, h_tab[0]); break;
        case 3: launch_pdl(conv_kernel, DM / CV_CPB, CV_THREADS, CV_SMEM, 0, (const uint4*)h_sym[7], (const float4*)h_sym[4], (const bf16*)h_sym[8], (bf16*)h_sym[9], (const uint4*)h_sym[0], h_tmOut); break;
        case 5: launch_pdl(a1, h_nsm, A1_THREADS, A1_SMEM, par, h_tmX1, h_tmR1, h_tmX1st, h_tmW, h_tab[1]); break;
        case 7: launch_pdl(conv_kernel, DM / CV_CPB, CV_THREADS, CV_SMEM, 1, (const uint4*)h_sym[7] + SEQ / 8, (const float4*)h_sym[4] + SEQ / 2, (const bf16*)h_sym[8], (bf16*)h_sym[10], (const uint4*)h_sym[0], h_tmOut); break;
        default: break;
    }
}
static int n_stage_kernels() { return 9; }
static const char* stage_name(int k) { const char* n[] = {"kgen", "a1", "a2", "conv", "tr", "a1", "a2", "conv", "tr"}; return n[k]; }

extern "C" void kernel_launch(void* const* d_in, const int* in_sizes, int n_in, void* d_out, int out_size) {
    (void)in_sizes; (void)n_in; (void)out_size;
    static const void *p_in = nullptr, *p_w1 = nullptr, *p_w2 = nullptr, *p_out = nullptr;
    if (p_in != d_in[0] || p_w1 != d_in[1] || p_w2 != d_in[2] || p_out != d_out) {
        cudaFuncSetAttribute(conv_kernel, cudaFuncAttributeMaxDynamicSharedMemorySize, CV_SMEM);
        cudaFuncSetAttribute(a1_kernel<true>, cudaFuncAttributeMaxDynamicSharedMemorySize, A1_SMEM);
        cudaFuncSetAttribute(a1_kernel<false>, cudaFuncAttributeMaxDynamicSharedMemorySize, A1_SMEM);
        int dev; cudaGetDevice(&dev); cudaDeviceGetAttribute(&h_nsm, cudaDevAttrMultiProcessorCount, dev);
        if (h_nsm != 132) h_nsm = 128;
        cudaGetSymbolAddress(&h_sym[0], g_tap); cudaGetSymbolAddress(&h_sym[1], g_wq); cudaGetSymbolAddress(&h_sym[2], g_wo);
        cudaGetSymbolAddress(&h_sym[3], g_halo); cudaGetSymbolAddress(&h_sym[4], g_sum); cudaGetSymbolAddress(&h_sym[5], g_csp); cudaGetSymbolAddress(&h_sym[6], g_of);
        cudaGetSymbolAddress(&h_sym[7], g_piv); cudaGetSymbolAddress(&h_sym[8], g_x1T); cudaGetSymbolAddress(&h_sym[9], g_xcT); cudaGetSymbolAddress(&h_sym[10], g_yT);
        for (int i = 0; i < 264; i++) {
            const int s = i % 132, h = (s - 64) >> 1;
            const int t = h_nsm != 132 ? s : s < 64 ? ((s >> 1) & 7) * 16 + (s >> 4) * 2 + (s & 1) : s < 120 ? (1 + h % 7) * 16 + 8 + (h / 7) * 2 + (s & 1) : s < 124 ? 128 : s - 116;
            const int hg = (4 * (t >> 6) + (t & 3)) & 7;
            const uint64_t wp = (uint64_t)h_sym[1] + hg * 10 * WQ_STAGE;
            h_tab[i / 132].e[s] = make_uint4((uint32_t)wp, (uint32_t)(wp >> 32), ((t >> 2) & 15) | (i / 132) << 4 | hg << 8 | 5 * (hg >> 2) << 16 | (uint32_t)t << 24, 0);
        }
        void *px1, *px2;
        cudaGetSymbolAddress(&px1, g_x1T); cudaGetSymbolAddress(&px2, g_xcT);
        make_tmap(&h_tmX0, d_in[0], 128 * 640, 64, 64, 64, CU_TENSOR_MAP_SWIZZLE_128B, 1280, 640, 0);
        make_tmap(&h_tmX1, px2, 128, 64 * XCP, 64, 64, CU_TENSOR_MAP_SWIZZLE_128B, XCP, 64, 0);
        make_tmap(&h_tmR0, d_in[0], 640, 1024, 80, 64, CU_TENSOR_MAP_SWIZZLE_NONE, 1280, 640, 1);
        make_tmap(&h_tmR1, px2, 64, 640, 64, 80, CU_TENSOR_MAP_SWIZZLE_128B, XCP, 64, 1);
        make_tmap(&h_tmX1st, px1, 2048, 640, 64, 80, CU_TENSOR_MAP_SWIZZLE_128B, XCP);
        make_tmap(&h_tmW.q, d_in[1], 16, 640, 16, 32, CU_TENSOR_MAP_SWIZZLE_32B, 1920, 16, 5);
        make_tmap(&h_tmW.o, d_in[2], 640, 640, 4, 0, CU_TENSOR_MAP_SWIZZLE_32B);
        make_tmap(&h_tmW.t, d_in[2], 640, 640, 2, 0, CU_TENSOR_MAP_SWIZZLE_32B);
        make_tmap(&h_tmOut, d_out, 640, 1024, 80, 8, CU_TENSOR_MAP_SWIZZLE_NONE, 1280, 640, 1);
        p_in = d_in[0]; p_w1 = d_in[1]; p_w2 = d_in[2]; p_out = d_out;
    }
    for (int k = 0; k < n_stage_kernels(); k++) launch_stage(k, d_in, d_out);
}
```

```cpp
#include <cuda_runtime.h>
#include <cuda_bf16.h>
#include <cuda_fp16.h>
#include <stdint.h>
#include <cuda.h>

typedef __nv_bfloat16 bf16;

constexpr int SEQ = 2048;
constexpr int DM = 640;
constexpr int NMODE = 192;

__device__ __forceinline__ float bf2f(bf16 v) { return __bfloat162float(v); }
__device__ __forceinline__ float rbf(float v) {
    uint32_t r;
    asm("cvt.rn.bf16x2.f32 %0, %1, %2;" : "=r"(r) : "f"(v), "f"(0.f));
    return __uint_as_float(r);
}
__device__ __forceinline__ uint32_t pack2(float lo, float hi) {
    __nv_bfloat162 t = __floats2bfloat162_rn(lo, hi);
    return *reinterpret_cast<uint32_t*>(&t);
}
__device__ __forceinline__ void pdl_sync() {
    asm volatile("griddepcontrol.wait;" ::: "memory");
    asm volatile("griddepcontrol.launch_dependents;" ::: "memory");
}
__device__ __forceinline__ float sqrt_apx(float v) { float r; asm("sqrt.approx.ftz.f32 %0, %1;" : "=f"(r) : "f"(v)); return r; }
__device__ __forceinline__ float rcp_apx(float v) { float r; asm("rcp.approx.ftz.f32 %0, %1;" : "=f"(r) : "f"(v)); return r; }
__device__ __forceinline__ uint32_t smem_u32(const void* p) { return (uint32_t)__cvta_generic_to_shared(p); }

constexpr int TAPB = 2944, TAPE = 928;
__device__ __align__(128) uint4 g_tap[DM * TAPB / 16];
#define XPAD 64
constexpr int XCP = SEQ + XPAD;
__device__ __align__(128) bf16 g_x1T[DM * XCP];
__device__ __align__(128) bf16 g_xcT[DM * XCP];
__device__ __align__(128) uint4 g_of[128 * 1280];
constexpr int WQ_STAGE = 240 * 128, WOB = 80 * 160;
__device__ __align__(128) uint4 g_wq[8 * 10 * WQ_STAGE / 16];
__device__ __align__(128) uint4 g_wo[64 * WOB / 16];
__device__ __align__(128) uint4 g_xb[128 * 240];
__device__ __align__(16) float g_csp[10 * 1920];
#define FSTR 32
__device__ __align__(128) float2 g_sum[2 * SEQ + 256 * FSTR];
__device__ __align__(16) bf16 g_piv[2 * SEQ];
__device__ __align__(128) bf16 g_yT[DM * XCP];
__device__ uint32_t g_epoch;
__device__ __align__(16) unsigned long long g_rstat[SEQ];
__device__ __align__(128) uint4 g_halo[640 * 148];
__device__ __forceinline__ unsigned long long tagw(uint32_t payload, uint32_t tag) { return ((unsigned long long)tag << 32) | payload; }
__device__ __forceinline__ ulonglong2 ld_tag2(const ulonglong2* p) {
    ulonglong2 v;
    asm volatile("ld.relaxed.gpu.global.v2.u64 {%0, %1}, [%2];" : "=l"(v.x), "=l"(v.y) : "l"(p) : "memory");
    return v;
}
__device__ __forceinline__ bool tag_ok(ulonglong2 v, uint32_t tag) { return (uint32_t)(v.x >> 32) == tag && (uint32_t)(v.y >> 32) == tag; }
__device__ __forceinline__ uint32_t ld_epoch() { uint32_t v; asm volatile("ld.relaxed.gpu.global.u32 %0, [%1];" : "=r"(v) : "l"(&g_epoch) : "memory"); return v + 1; }
constexpr int SPIN_MAX = 1 << 20;
__device__ __align__(128) uint32_t g_started[11 * 32];
__device__ __forceinline__ void sm_started(int slot) { asm volatile("red.relaxed.gpu.global.add.u32 [%0], 1;" ::"l"(g_started + slot) : "memory"); }
__device__ __forceinline__ void publish(int slot) {
    asm volatile("fence.proxy.async.global;" ::: "memory");
    asm volatile("red.release.gpu.global.add.u32 [%0], 1;" ::"l"(g_started + slot) : "memory");
}
__device__ __forceinline__ void await_all(int slot, uint32_t want) {
#pragma unroll 1
    for (int it = 0; it < SPIN_MAX; it++) {
        uint32_t v;
        asm volatile("ld.acquire.gpu.global.u32 %0, [%1];" : "=r"(v) : "l"(g_started + slot) : "memory");
        if (__all_sync(~0u, (int)(v - want) >= 0)) break;
        __nanosleep(50);
    }
    asm volatile("fence.proxy.async.global;" ::: "memory");
}
__device__ __noinline__ void sm_idle(int slot) {
    if (threadIdx.x != 288) return;
    asm volatile("fence.acq_rel.gpu;" ::: "memory");
    asm volatile("fence.proxy.async.global;" ::: "memory");
    sm_started(slot);
    const uint32_t want = ld_epoch() * gridDim.x;
    pdl_sync();
#pragma unroll 1
    for (int it = 0; it < SPIN_MAX; it++) {
        uint32_t v;
        asm volatile("ld.relaxed.gpu.global.u32 %0, [%1];" : "=r"(v) : "l"(g_started + slot) : "memory");
        if ((int)(v - want) >= 0) break;
        __nanosleep(100);
    }
}
struct TileTab { uint4 e[132]; };
__device__ __forceinline__ bool elect() {
    uint32_t p;
    asm volatile("{\n.reg .pred p;\nelect.sync _|p, 0xffffffff;\nselp.b32 %0, 1, 0, p;\n}" : "=r"(p));
    return p;
}
#define DBG_SYMS
#define TSTAMP(i)
#define TSTAMP1(i)
#define TSTAMP1T(i, t)
#define TSTAMP1X(i, t)
#define SPAN(k, i)
#define GSTAMP(arr, i)
#define TSTAMP2(i)
#define TSTAMP3(i)
#define TSTAMP4(i)
#define TSTAMPK(i, t)
#define TSTAMPC(i)
#define DBGC(i)
#define DBGV(i, v)
#define DBGCAL(i)

#define CSK(i)
#define CSK_END
#define CSA(i)
#define CSA_END
#define CST(i)
#define CST_END
#define CST_EXTRA 0
__device__ __forceinline__ void mma_bf16(float* d, uint32_t a0, uint32_t a1, uint32_t a2, uint32_t a3, uint32_t b0, uint32_t b1) {
    asm volatile("mma.sync.aligned.m16n8k16.row.col.f32.bf16.bf16.f32 {%0,%1,%2,%3}, {%4,%5,%6,%7}, {%8,%9}, {%0,%1,%2,%3};"
                 : "+f"(d[0]), "+f"(d[1]), "+f"(d[2]), "+f"(d[3]) : "r"(a0), "r"(a1), "r"(a2), "r"(a3), "r"(b0), "r"(b1));
}
__device__ __forceinline__ void mma_bf16_k8(float* d, uint32_t a0, uint32_t a1, uint32_t b0) {
    asm volatile("mma.sync.aligned.m16n8k8.row.col.f32.bf16.bf16.f32 {%0,%1,%2,%3}, {%4,%5}, {%6}, {%0,%1,%2,%3};"
                 : "+f"(d[0]), "+f"(d[1]), "+f"(d[2]), "+f"(d[3]) : "r"(a0), "r"(a1), "r"(b0));
}
__device__ __forceinline__ void ldsm_x4(uint32_t* r, uint32_t addr) {
    asm volatile("ldmatrix.sync.aligned.m8n8.x4.shared.b16 {%0,%1,%2,%3}, [%4];"
                 : "=r"(r[0]), "=r"(r[1]), "=r"(r[2]), "=r"(r[3]) : "r"(addr));
}

__device__ __forceinline__ void ldsm_x4_t(uint32_t* r, uint32_t addr) {
    asm volatile("ldmatrix.sync.aligned.m8n8.x4.trans.shared.b16 {%0,%1,%2,%3}, [%4];"
                 : "=r"(r[0]), "=r"(r[1]), "=r"(r[2]), "=r"(r[3]) : "r"(addr));
}
__device__ __forceinline__ void mbar_init(uint32_t bar, int count) { asm volatile("mbarrier.init.shared::cta.b64 [%0], %1;" ::"r"(bar), "r"(count)); }
__device__ __forceinline__ void mbar_arrive(uint32_t bar) { asm volatile("mbarrier.arrive.shared::cta.b64 _, [%0];" ::"r"(bar) : "memory"); }
__device__ __forceinline__ void mbar_wait(uint32_t bar, uint32_t parity) {
    asm volatile("{\n.reg .pred p;\nWAIT_LOOP:\n"
                 "mbarrier.try_wait.parity.shared::cta.b64 p, [%0], %1;\n"
                 "@p bra.uni WAIT_DONE;\nbra.uni WAIT_LOOP;\nWAIT_DONE:\n}" ::"r"(bar), "r"(parity) : "memory");
}

__device__ __forceinline__ void mbar_expect_tx(uint32_t bar, uint32_t bytes) {
    asm volatile("mbarrier.arrive.expect_tx.shared::cta.b64 _, [%0], %1;" ::"r"(bar), "r"(bytes) : "memory");
}
__device__ __forceinline__ void tma_load_2d(uint32_t dst, const void* tmap, int c0, int c1, uint32_t bar) {
    asm volatile("cp.async.bulk.tensor.2d.shared::cluster.global.mbarrier::complete_tx::bytes [%0], [%1, {%3, %4}], [%2];"
                 ::"r"(dst), "l"(tmap), "r"(bar), "r"(c0), "r"(c1) : "memory");
}
__device__ __forceinline__ void tma_load_3d(uint32_t dst, const void* tmap, int c0, int c1, int c2, uint32_t bar) {
    asm volatile("cp.async.bulk.tensor.3d.shared::cluster.global.mbarrier::complete_tx::bytes [%0], [%1, {%3, %4, %5}], [%2];"
                 ::"r"(dst), "l"(tmap), "r"(bar), "r"(c0), "r"(c1), "r"(c2) : "memory");
}
__device__ __forceinline__ void fence_async_smem() { asm volatile("fence.proxy.async.shared::cta;" ::: "memory"); }
__device__ __forceinline__ void bulk_load(uint32_t dst, const void* src, uint32_t bytes, uint32_t bar) {
    asm volatile("cp.async.bulk.shared::cluster.global.mbarrier::complete_tx::bytes [%0], [%1], %2, [%3];"
                 ::"r"(dst), "l"(src), "r"(bytes), "r"(bar) : "memory");
}
__device__ __forceinline__ void stsm_x4(uint32_t addr, uint32_t r0, uint32_t r1, uint32_t r2, uint32_t r3) {
    asm volatile("stmatrix.sync.aligned.m8n8.x4.shared.b16 [%0], {%1,%2,%3,%4};" ::"r"(addr), "r"(r0), "r"(r1), "r"(r2), "r"(r3) : "memory");
}
__device__ __forceinline__ void stsm_x4_t(uint32_t addr, uint32_t r0, uint32_t r1, uint32_t r2, uint32_t r3) {
    asm volatile("stmatrix.sync.aligned.m8n8.x4.trans.shared.b16 [%0], {%1,%2,%3,%4};" ::"r"(addr), "r"(r0), "r"(r1), "r"(r2), "r"(r3) : "memory");
}
__device__ __forceinline__ void prefetch_tmap(const void* tmap) { asm volatile("prefetch.tensormap [%0];" ::"l"(tmap) : "memory"); }

__device__ __forceinline__ float2 cexp_at(float wr2, float wi, float p) {
    float er;
    asm("ex2.approx.ftz.f32 %0, %1;" : "=f"(er) : "f"(wr2 * p));
    float th = wi * p;
    const float k = rintf(th * 0.15915494309189535f);
    th = fmaf(k, -6.2831854820251465f, th);
    th = fmaf(k, 1.7484555314695172e-7f, th);
    return make_float2(er * __cosf(th), er * __sinf(th));
}
__device__ __forceinline__ float2 cmul(float2 a, float2 b) {
    return make_float2(fmaf(a.x, b.x, -a.y * b.y), fmaf(a.x, b.y, a.y * b.x));
}
__device__ __forceinline__ float2 csqr(float2 a) { return make_float2(fmaf(a.x, a.x, -a.y * a.y), (a.x + a.x) * a.y); }
__device__ __forceinline__ uint32_t packh(float2 v) {
    uint32_t r;
    asm("cvt.rn.f16x2.f32 %0, %1, %2;" : "=r"(r) : "f"(v.y), "f"(v.x));
    return r;
}
__device__ __forceinline__ uint2 packr(float2 v) { return make_uint2(packh(v), packh(make_float2(-v.y, v.x))); }
__device__ __forceinline__ uint32_t hcmul(uint32_t a, uint2 b) {
    const __half2 x = *reinterpret_cast<const __half2*>(&a);
    const __half2 r = __hfma2(__high2half2(x), *reinterpret_cast<const __half2*>(&b.y), __hmul2(__low2half2(x), *reinterpret_cast<const __half2*>(&b.x)));
    return *reinterpret_cast<const uint32_t*>(&r);
}

struct Par { const bf16 *logA, *Aim, *Cre, *Cim, *logdt, *dsk; int layer, pad; const bf16* x; uint4 *sum, *wop, *of, *halo, *tap; float* csp; uint4* wq; const bf16 *wqkv, *wo; };
struct KgMaps { CUtensorMap q, o, t; };

__device__ __forceinline__ void bulk_prefetch(const void* p, uint32_t bytes) { asm volatile("cp.async.bulk.prefetch.L2.global [%0], %1;" ::"l"(p), "r"(bytes) : "memory"); }
__device__ __forceinline__ void bulk_store(void* dst, uint32_t src, uint32_t bytes) { asm volatile("cp.async.bulk.global.shared::cta.bulk_group [%0], [%1], %2;" ::"l"(dst), "r"(src), "r"(bytes) : "memory"); }
__device__ __forceinline__ void kgen_first(const Par& in, const KgMaps& tm, const uint32_t b0, const uint32_t wbar, const bool one) {
    const uint32_t blk = blockIdx.x, sec = (blk >= 40) + (blk >= 80), it = (blk >> 3) - 5 * sec, up = (blk >> 2) & 1, hi = blk >> 6;
    auto fetch = [&](int h) {
        if (blk < 120) asm volatile("cp.async.bulk.tensor.4d.shared::cluster.global.mbarrier::complete_tx::bytes [%0], [%1, {%3, %3, %4, %5}], [%2];"
                                    ::"r"(b0 + 10240 * h), "l"(&tm.q), "r"(wbar + 8 * h), "r"(0), "r"(sec * 40 + (blk & 7) * 5), "r"(2 * it + 10 * (up ^ h)) : "memory");
    };
    auto fetch_o = [&](int i) {
        asm volatile("cp.async.bulk.tensor.5d.shared::cluster.global.mbarrier::complete_tx::bytes [%0], [%1, {%3, %3, %4, %3, %5}], [%2];"
                     ::"r"(b0 + 20480 + i * 5120), "l"(&tm.o + i), "r"(wbar + 16), "r"(0), "r"((blk & 7) * 10 + (hi + i) * 4), "r"(((blk >> 3) & 7) * 5) : "memory");
    };
    if (one) {
#pragma unroll
        for (int i = 0; i < 3; i++) mbar_init(wbar + 8 * i, 1);
        asm volatile("fence.mbarrier_init.release.cluster;" ::: "memory");
        fetch(0);
    }
    __syncwarp();
    if (blk >> 20) __trap();
    if (one) {
        bulk_prefetch(in.wqkv + blk * 9600, 19200);
        fetch(1);
        bulk_prefetch(in.wo + blk * 3200, 6400);
        fetch_o(0);
        if (hi) fetch_o(1);
        mbar_expect_tx(wbar, 10240); mbar_expect_tx(wbar + 8, 10240); mbar_expect_tx(wbar + 16, 5120 + hi * 2560);
        bulk_prefetch(in.x + blk * 10240, 20480);
    }
}
__device__ __forceinline__ void kgen_side(const Par& in, const uint32_t b0, const uint32_t wbar) {
    const uint32_t blk = blockIdx.x, sec = (blk >= 40) + (blk >= 80), it = (blk >> 3) - 5 * sec, cg = (blk >> 3) & 7, hb = blk & 7;
    unsigned char* dst = reinterpret_cast<unsigned char*>(in.wq) + (hb * 10 + it) * WQ_STAGE + sec * 5120;
    if (blk < 120) {
        mbar_wait(wbar, 0);
        CSK(2);
        bulk_store(dst, b0, 5120); bulk_store(dst + 15360, b0 + 5120, 5120);
        mbar_wait(wbar + 8, 0);
        CSK(3);
        bulk_store(dst + 5 * WQ_STAGE, b0 + 10240, 5120); bulk_store(dst + 5 * WQ_STAGE + 15360, b0 + 15360, 5120);
        asm volatile("cp.async.bulk.commit_group;" ::: "memory");
        asm volatile("cp.async.bulk.wait_group 0;" ::: "memory");
        CSK(4);
        publish(96 + 32 * hb);
        CSK(5);
    }
    if (blk < 128) {
        mbar_wait(wbar + 16, 0);
        bulk_store(reinterpret_cast<unsigned char*>(in.wop) + (cg * 8 + (hb == cg ? 0 : hb + (hb < cg))) * WOB + (blk >> 6) * 5120, b0 + 20480, blk < 64 ? 5120 : 7680);
        asm volatile("cp.async.bulk.commit_group;" ::: "memory");
    }
}
__device__ __forceinline__ void kgen_sums(const Par& in, const uint32_t b0, const int h) {
    const int lane = threadIdx.x & 31, blk = blockIdx.x;
    if (blk < 120) {
        float cs[5][4] = {};
#pragma unroll
        for (int a = 0; a < 4; a++)
#pragma unroll
            for (int j = 0; j < 5; j++) {
                uint32_t w[4];
                ldsm_x4_t(w, b0 + h * 10240 + j * 1024 + ((lane >> 4) * 8 + (lane & 7)) * 32 + ((((lane >> 3) ^ (lane >> 2)) & 1) << 4) + (a >> 1) * 5120 + (a & 1) * 512);
                mma_bf16(cs[j], w[0], w[1], w[2], w[3], 0x3f803f80u, 0x3f803f80u);
            }
#pragma unroll
        for (int j = 0; j < 5; j++)
            if ((lane & 3) < 2) in.csp[(blk + 120 * h) * 80 + j * 16 + (lane >> 2) + 8 * (lane & 3)] = (lane & 3) ? cs[j][2] : cs[j][0];
    }
}
struct KgPar { uint32_t pw[4], ph[4], pdt, pdsk; };
__device__ __forceinline__ void kgen_load(const Par& in, const bf16* logA, const int w11, KgPar& k) {
    const uint32_t o = blockIdx.x * 480 + min(w11 * 48, w11 * 32 + 128), ow = o + (threadIdx.x & 31), oh = o + ow + (w11 < 8 ? 64 : 0);
    k.pdt = reinterpret_cast<const unsigned short*>(in.logdt)[ow / 96];
    k.pdsk = reinterpret_cast<const unsigned short*>(in.dsk)[ow / 96];
#pragma unroll
    for (int i = 0; i < 4; i++) {
        const bf16* p = i == 0 ? logA : i == 1 ? in.Aim : i == 2 ? in.Cre : in.Cim;
        k.pw[i] = reinterpret_cast<const uint32_t*>(p)[ow]; k.ph[i] = reinterpret_cast<const unsigned short*>(p)[oh];
    }
}
__device__ __forceinline__ void kgen_tables(const Par& in, uint4* tabs, const int w11, const KgPar& kp) {
    const int lane = threadIdx.x & 31, grp = min(w11 >> 1, 4), warp = w11 - 2 * grp;
    const int blk = blockIdx.x, d = blk * 5 + grp, tid = warp * 32 + lane;
    uint4* tab = tabs + grp * (2 * 256);
    const uint32_t *pw = kp.pw, *ph = kp.ph;
#pragma unroll
    for (int i = 0; i < 3; i++)
        if (i < 2 || w11 * 32 + lane < 36) asm volatile("st.global.v4.u32 [%0], {%1,%1,%1,%1};" ::"l"(in.halo + blk * 740 + w11 * 32 + lane + 352 * i), "r"(~0u));
    __syncwarp();
    if (w11 == 10) {
        if (lane < 16) in.sum[blk * 16 + lane] = make_uint4(0, 0, 0, 0);
        else if (lane < 20) reinterpret_cast<uint32_t*>(in.sum + 2048)[(blk * 4 + lane - 16) * FSTR] = 0;
    } else if (w11 > 1) asm volatile("bar.arrive 9, 352;" ::: "memory");
#pragma unroll
    for (int i = 0; i < 6; i++) tabs[w11 * 256 + 32 * i + lane] = make_uint4(0, 0, 0, 0);
    __syncwarp();
    CSK(1);
    const uint32_t tw = smem_u32(tabs) + w11 * 4096;
    const int g = lane >> 2, t = lane & 3;
    const int mt = lane >> 3, r = lane & 7;
    const uint32_t st1 = tw + mt * 1024 + r * 16, st2 = tw + (mt & 1) * 1024 + (mt >> 1) * 128 + ((r ^ (mt >> 1)) << 4), st3 = tw + 2048 + mt * 128 + ((r ^ mt) << 4);
    const uint32_t lda = tw + (mt & 1) * 1024 + r * 128 + (((mt >> 1) ^ r) << 4), ldb = tw + (mt >> 1) * 1024 + r * 128 + (((mt & 1) ^ r) << 4), ldc = tw + 2048 + r * 128 + ((mt ^ r) << 4);
    auto ldsm = [](uint32_t* v, uint32_t a) {
        asm volatile("ldmatrix.sync.aligned.m8n8.x4.shared.b16 {%0,%1,%2,%3}, [%4];" : "=r"(v[0]), "=r"(v[1]), "=r"(v[2]), "=r"(v[3]) : "r"(a) : "memory");
    };
    auto mma = [](float* c, const uint32_t* a, const uint32_t* b) {
        asm("mma.sync.aligned.m16n8k16.row.col.f32.f16.f16.f32 {%0,%1,%2,%3}, {%4,%5,%6,%7}, {%8,%9}, {%0,%1,%2,%3};"
            : "+f"(c[0]), "+f"(c[1]), "+f"(c[2]), "+f"(c[3]) : "r"(a[0]), "r"(a[1]), "r"(a[2]), "r"(a[3]), "r"(b[0]), "r"(b[1]));
    };
    asm volatile("st.shared.u32 [%0], %1;" ::"r"(tw + 3072), "r"(st1 ^ st2 ^ st3 ^ lda ^ ldb ^ ldc) : "memory");
    if (in.pad) __trap();
    const float dt = rbf(expf(__uint_as_float(kp.pdt << 16)));
    const uint32_t cm = __vmaxu2(__vmaxu2(pw[2] & 0x7fff7fffu, pw[3] & 0x7fff7fffu), __byte_perm(ph[2], ph[3], 0x5410) & 0x7fff7fffu);
    const int ex = min(max((int)(__float_as_uint(__uint_as_float(__reduce_max_sync(~0u, max(cm << 16, cm & 0xffff0000u))) * dt) >> 23), 20), 240);
    const float scale = __uint_as_float((uint32_t)(127 + 10 + 127 - ex) << 23), unscale = 2.0f * __uint_as_float((uint32_t)(ex - 10) << 23);
    float k2048 = 0.f;
    float acc[5][4] = {};
    uint32_t af[4][4] = {};
    auto rest = [&] {
        uint32_t b[4][4], c[8];
#pragma unroll
        for (int k = 0; k < 4; k++) {
            ldsm(b[k], ldb ^ (k << 5));
            if (!(k & 1)) ldsm(c + 2 * k, ldc ^ (k << 5));
        }
#pragma unroll
        for (int k = 0; k < 4; k++) { mma(acc[2], af[k], b[k]); mma(acc[3], af[k], b[k] + 2); mma(acc[4], af[k], c + 2 * k); }
    };
#pragma unroll 1
    for (uint32_t sel = 0x1076; sel < (grp < 4 ? 0x6000u : 0x4000u); sel += 0x2200) {
        rest();
        auto par = [&](int i) { return __uint_as_float(__byte_perm(pw[i], ph[i], sel)); };
        const float wr2 = -rbf(expf(par(0))) * dt * 1.4426950408889634f, wi = par(1) * dt;
        const float2 y1 = cexp_at(wr2, -wi, 1.f), w64 = cexp_at(wr2, wi, 64.f), y4 = csqr(csqr(y1)), z8 = csqr(make_float2(y4.x, -y4.y)), y128 = csqr(make_float2(w64.x, -w64.y));
        float2 h0 = make_float2(1.f, 0.f), g0 = make_float2(par(2) * dt * scale, -par(3) * dt * scale);
        const float2 v2 = csqr(y128), v3 = cmul(v2, y128), v4 = csqr(v2), v8 = csqr(v4), c8 = cmul(g0, v8);
        const uint2 z64 = packr(w64), v[8] = {make_uint2(packh(c8), 0u), packr(y128), packr(v2), packr(v3), packr(v4), packr(cmul(v4, y128)), packr(csqr(v3)), packr(cmul(v4, v3))};
        k2048 += fmaf(c8.x, v8.x, -c8.y * v8.y);
        uint32_t ge[4];
#pragma unroll
        for (int e = 0; e < 8; e++) {
            const uint32_t p = packh(h0), q = packh(g0);
            if (!(e & 1)) ge[e >> 1] = q;
            stsm_x4((st1 ^ (e << 4)) + e * 128, p, e ? hcmul(p, z64) : z64.x, q, hcmul(q, v[1]));
            if (e < 7) { h0 = e ? cmul(h0, z8) : z8; g0 = cmul(g0, y1); }
        }
        __syncwarp();
        uint32_t b[4][4];
#pragma unroll
        for (int k = 0; k < 4; k++) { ldsm(af[k], lda ^ (k << 5)); ldsm(b[k], (ldb ^ (k << 5)) + 2048); }
#pragma unroll
        for (int e = 0; e < 8; e += 2) {
            stsm_x4((st2 ^ (e << 4)) + e * 128, hcmul(ge[e & 3], v[2 + (e >> 2)]), hcmul(ge[0], v[4 + (e >> 1)]), hcmul(ge[(e & 3) + 1], v[2 + (e >> 2)]), hcmul(ge[2], v[4 + (e >> 1)]));
            if (!(e & 3)) stsm_x4((st3 ^ (e << 4)) + e * 128, e ? hcmul(v[0].x, v[e]) : v[0].x, hcmul(v[0].x, v[e + 1]), hcmul(v[0].x, v[e + 2]), hcmul(v[0].x, v[e + 3]));
            mma(acc[0], af[e >> 1], b[e >> 1]);
            mma(acc[1], af[e >> 1], b[e >> 1] + 2);
        }
        __syncwarp();
        if (sel == 0x1076) CSK(3);
    }
    rest();
#pragma unroll
    for (int e = 0; e < 5; e++) k2048 += __shfl_xor_sync(~0u, k2048, 1 << e);
    {
        float* Pp = reinterpret_cast<float*>(tab + warp * 256);
        auto sw = [](int i) { return i ^ ((i >> 2) & 24); };
#pragma unroll
        for (int h = 0; h < 2; h++) {
            const int b = g + 8 * h;
            *reinterpret_cast<float2*>(Pp + sw(8 * b + 2 * t)) = make_float2(acc[0][2 * h] * unscale, acc[0][2 * h + 1] * unscale);
            *reinterpret_cast<float2*>(Pp + 128 + sw(8 * b + 2 * t)) = make_float2(acc[1][2 * h] * unscale, acc[1][2 * h + 1] * unscale);
            *reinterpret_cast<float2*>(Pp + 256 + sw(4 * b + 2 * (t & 1) + 64 * (t >> 1))) = make_float2(acc[2][2 * h] * unscale, acc[2][2 * h + 1] * unscale);
            *reinterpret_cast<float2*>(Pp + 384 + sw(2 * b + 32 * t)) = make_float2(acc[3][2 * h] * unscale, acc[3][2 * h + 1] * unscale);
            Pp[512 + sw(b + 32 * t)] = acc[4][2 * h] * unscale;
            Pp[512 + sw(b + 32 * t + 16)] = acc[4][2 * h + 1] * unscale;
        }
        if (lane == 0) Pp[640] = k2048 * unscale;
    }
    CSK(4);
    asm volatile("bar.sync %0, %1;" ::"r"(grp + 4), "r"(grp < 4 ? 64 : 96) : "memory");
    if (warp == 2) return;
    const float* Kp = reinterpret_cast<const float*>(tab);
    auto ksum = [&](int i) -> float { return rbf(Kp[i] + Kp[1024 + i] + (grp < 4 ? 0.f : Kp[2048 + i])); };
    auto ksum2 = [&](int q) -> float2 {
        q ^= (q >> 2) & 12;
        const float2 a = reinterpret_cast<const float2*>(Kp)[q], b = reinterpret_cast<const float2*>(Kp)[512 + q];
        const float2 c = grp < 4 ? make_float2(0.f, 0.f) : reinterpret_cast<const float2*>(Kp)[1024 + q];
        return make_float2(a.x + b.x + c.x, a.y + b.y + c.y);
    };
    {
        uint2* W2 = reinterpret_cast<uint2*>(in.tap + d * (TAPB / 16)) + 8;
        uint2* E4 = W2 + (TAPE - 64) / 8;
        float2 v = ksum2(64 * warp + lane), z = ksum2(64 * warp + 32 + lane), y = ksum2(128 + tid);
        const int q = (96 + tid) ^ (((96 + tid) >> 2) & 6);
        const float4 ua = reinterpret_cast<const float4*>(Kp)[q], uc = reinterpret_cast<const float4*>(Kp)[256 + q], ud = grp < 4 ? make_float4(0.f, 0.f, 0.f, 0.f) : reinterpret_cast<const float4*>(Kp)[512 + q];
        const float4 ub = make_float4(uc.x + ud.x, uc.y + ud.y, uc.z + ud.z, uc.w + ud.w);
        const float s1 = ksum(tid == 31 ? 336 : lane ? 384 : 103), s2 = ksum(tid == 31 ? 512 : tid ? 640 : 231);
        if (tid == 0) v.x += __uint_as_float(kp.pdsk << 16);
        if (tid == 63) y.y -= s1;
        const uint32_t lo = pack2(v.x, v.y), hi = pack2(z.x, z.y), tp = pack2(y.x, y.y);
        uint32_t nl = __shfl_sync(~0u, lo, lane - 1), nh = __shfl_sync(~0u, lane == 31 ? lo : hi, lane - 1), nt = __shfl_sync(~0u, tp, lane + 1);
        if (lane == 0) nl = warp ? __float_as_uint(s1) : 0u;
        if (lane == 31) nt = warp ? 0u : __float_as_uint(s1) >> 16;
        W2[64 * warp + lane] = make_uint2(__byte_perm(lo, nl, 0x7610), __byte_perm(lo, 0, 0x1032));
        W2[64 * warp + lane + 32] = make_uint2(__byte_perm(hi, nh, 0x7610), __byte_perm(hi, 0, 0x1032));
        reinterpret_cast<uint4*>(W2)[64 + tid] = make_uint4(__byte_perm(tp, __float_as_uint(s2), tid ? 0x1010 : 0x7610), __byte_perm(tp, 0, 0x1010), __byte_perm(tp, 0, 0x1032), __byte_perm(nt, tp, 0x7610));
        E4[(tid < 32 ? 159 : 209 - 32) + tid] = make_uint2(pack2(ua.x + ub.x, ua.y + ub.y), pack2(ua.z + ub.z, ua.w + ub.w - (tid == 31 ? s2 : 0.f)));
        if (tid == 63) E4[241] = make_uint2(__float_as_uint(s2) >> 16, 0u);
    }
    CSK(5);
    SPAN(0, 3);
}

#define CV_SLEEP 40
#define CV_LD "ld.relaxed.gpu.global"
#define CV_NL 1
#define CV_D2 3
#define CV_PDH 12
#define CV_PDF 4
#define CV_HAND 7
constexpr int CV_CPB = 5;
constexpr int CV_THREADS = 512;
constexpr int UPADF = 128;
constexpr int ULEN = UPADF + SEQ;
constexpr int XLEN = XCP;
constexpr int BX_5 = 0, BX_3 = 3264, BX_9 = 6528, BX_7 = 8960, BX_LEN = 11392;
constexpr int CV_SM_U = 0;
constexpr int CV_SM_T = CV_CPB * ULEN * 2;
constexpr int CV_SM_B = CV_SM_T + CV_CPB * TAPB;
constexpr int CV_SM_X = CV_SM_B + CV_CPB * BX_LEN;
constexpr int CV_SM_Y = (CV_SM_X + CV_CPB * XLEN * 2 + 127) & ~127;
constexpr int CV_SM_CNT = CV_SM_Y + CV_CPB * 8192;
constexpr int CV_SM_O = CV_SM_CNT + 128;
constexpr int CV_SMEM = CV_SM_O + 20480 + CST_EXTRA;
static_assert(ULEN % 128 == 0 && CV_SM_B % 128 == 0 && CV_SM_CNT % 128 == 0, "layout");

__device__ __forceinline__ uint32_t sub2(uint32_t x, uint32_t m) {
    const __nv_bfloat162 d = __hsub2(*reinterpret_cast<const __nv_bfloat162*>(&x), *reinterpret_cast<const __nv_bfloat162*>(&m));
    return *reinterpret_cast<const uint32_t*>(&d);
}
__device__ __forceinline__ uint32_t add2(uint32_t x, uint32_t y) {
    const __nv_bfloat162 d = __hadd2_rn(*reinterpret_cast<const __nv_bfloat162*>(&x), *reinterpret_cast<const __nv_bfloat162*>(&y));
    return *reinterpret_cast<const uint32_t*>(&d);
}
__device__ __forceinline__ void wgmma_fence() { asm volatile("wgmma.fence.sync.aligned;" ::: "memory"); }
__device__ __forceinline__ void wgmma_commit() { asm volatile("wgmma.commit_group.sync.aligned;" ::: "memory"); }
template <int N> __device__ __forceinline__ void wgmma_wait() { asm volatile("wgmma.wait_group.sync.aligned %0;" ::"n"(N) : "memory"); }
__device__ __forceinline__ uint64_t make_desc(uint32_t addr, uint32_t lbo, uint32_t sbo, uint32_t mode) {
    return (uint64_t)((addr & 0x3FFFF) >> 4) | ((uint64_t)(lbo >> 4) << 16) | ((uint64_t)(sbo >> 4) << 32) | ((uint64_t)mode << 62);
}
__device__ __forceinline__ void wgmma_rs128(float (&d)[64], uint2 hi, uint2 lo, uint64_t db, int acc) {
    asm volatile("{\n.reg .pred p;\nsetp.ne.b32 p, %69, 0;\nwgmma.mma_async.sync.aligned.m64n128k16.f32.bf16.bf16 {%0,%1,%2,%3,%4,%5,%6,%7,%8,%9,%10,%11,%12,%13,%14,%15,%16,%17,%18,%19,%20,%21,%22,%23,%24,%25,%26,%27,%28,%29,%30,%31,%32,%33,%34,%35,%36,%37,%38,%39,%40,%41,%42,%43,%44,%45,%46,%47,%48,%49,%50,%51,%52,%53,%54,%55,%56,%57,%58,%59,%60,%61,%62,%63}, {%64,%65,%66,%67}, %68, p, 1, 1, 0;\n}"
                 : "+f"(d[0]), "+f"(d[1]), "+f"(d[2]), "+f"(d[3]), "+f"(d[4]), "+f"(d[5]), "+f"(d[6]), "+f"(d[7]), "+f"(d[8]), "+f"(d[9]), "+f"(d[10]), "+f"(d[11]), "+f"(d[12]), "+f"(d[13]), "+f"(d[14]), "+f"(d[15]), "+f"(d[16]), "+f"(d[17]), "+f"(d[18]), "+f"(d[19]), "+f"(d[20]), "+f"(d[21]), "+f"(d[22]), "+f"(d[23]), "+f"(d[24]), "+f"(d[25]), "+f"(d[26]), "+f"(d[27]), "+f"(d[28]), "+f"(d[29]), "+f"(d[30]), "+f"(d[31]), "+f"(d[32]), "+f"(d[33]), "+f"(d[34]), "+f"(d[35]), "+f"(d[36]), "+f"(d[37]), "+f"(d[38]), "+f"(d[39]), "+f"(d[40]), "+f"(d[41]), "+f"(d[42]), "+f"(d[43]), "+f"(d[44]), "+f"(d[45]), "+f"(d[46]), "+f"(d[47]), "+f"(d[48]), "+f"(d[49]), "+f"(d[50]), "+f"(d[51]), "+f"(d[52]), "+f"(d[53]), "+f"(d[54]), "+f"(d[55]), "+f"(d[56]), "+f"(d[57]), "+f"(d[58]), "+f"(d[59]), "+f"(d[60]), "+f"(d[61]), "+f"(d[62]), "+f"(d[63])
                 : "r"(hi.x), "r"(hi.y), "r"(lo.x), "r"(lo.y), "l"(db), "r"(acc));
}
template <int V> struct Int { __device__ constexpr operator int() const { return V; } };
__device__ __forceinline__ void sts4(uint32_t a, const uint32_t* v) { asm volatile("st.shared.v4.u32 [%0], {%1,%2,%3,%4};" ::"r"(a), "r"(v[0]), "r"(v[1]), "r"(v[2]), "r"(v[3]) : "memory"); }
__device__ __forceinline__ uint32_t lds1(uint32_t a) { uint32_t v; asm volatile("ld.shared.u32 %0, [%1];" : "=r"(v) : "r"(a) : "memory"); return v; }
__device__ __forceinline__ uint32_t lds1v(uint32_t a) { uint32_t v; asm volatile("ld.volatile.shared.u32 %0, [%1];" : "=r"(v) : "r"(a) : "memory"); return v; }
__device__ __forceinline__ uint4 lds4(uint32_t a) { uint4 v; asm volatile("ld.shared.v4.u32 {%0,%1,%2,%3}, [%4];" : "=r"(v.x), "=r"(v.y), "=r"(v.z), "=r"(v.w) : "r"(a) : "memory"); return v; }
__device__ __forceinline__ uint4 ldx(uint32_t a) {
    uint4 v;
    asm volatile("ld.shared.v2.u32 {%0,%1}, [%4];\nld.shared.v2.u32 {%2,%3}, [%4+128];" : "=r"(v.x), "=r"(v.y), "=r"(v.z), "=r"(v.w) : "r"(a) : "memory");
    return v;
}
__device__ __forceinline__ void cv_store(unsigned char* p, uint4 x, uint4 y) {
    asm volatile("st.relaxed.gpu.global.v2.u32 [%0], {%1,%2};" ::"l"(p), "r"(add2(x.x, __byte_perm(y.x, y.y, 0x5410))), "r"(add2(x.y, __byte_perm(y.z, y.w, 0x5410))) : "memory");
    asm volatile("st.relaxed.gpu.global.v2.u32 [%0], {%1,%2};" ::"l"(p + 128), "r"(add2(x.z, __byte_perm(y.x, y.y, 0x7632))), "r"(add2(x.w, __byte_perm(y.z, y.w, 0x7632))) : "memory");
}
__device__ __forceinline__ int usw(int ch) { return ch ^ ((ch >> 3) & 1); }
__global__ void __launch_bounds__(CV_THREADS, 1) conv_kernel(int layer, const uint4* __restrict__ piv, const float4* __restrict__ sum, const bf16* __restrict__ x1T,
                                                             bf16* __restrict__ dst, const uint4* __restrict__ tap, const __grid_constant__ CUtensorMap tmOut) {
    extern __shared__ __align__(1024) unsigned char sm[];
    SPAN(3 + 4 * layer, 0);
    bf16* Us = reinterpret_cast<bf16*>(sm + CV_SM_U);
    bf16* Xs = reinterpret_cast<bf16*>(sm + CV_SM_X);
#define CV_IDX int tid; asm volatile("mov.u32 %0, %tid.x;" : "=r"(tid)); const int lane = tid & 31, warp = __shfl_sync(~0u, tid >> 5, 0);
    const int d0 = blockIdx.x * CV_CPB, tile = blockIdx.x; (void)tile;
    const uint32_t cnt = smem_u32(sm + CV_SM_CNT);
    struct Lc { uint32_t a4, a8, uc, ud, y, e4, en, sp, ss; int go; };
    auto lane_consts = [&](int lane, int c) {
        const int mat = lane >> 3, r = lane & 7, g = lane >> 2, ti = lane & 3, e = g - 2 * ti;
        const int j2 = 13 + (r ^ 1) + 8 * (mat >> 1), j3 = j2 + 2, i0 = 8 * (mat & 1);
        const uint32_t sb = smem_u32(sm), oc = sb + usw(16 * (mat >> 1) + 2 * r + (mat & 1)) * 16;
        const Lc l = {sb + CV_SM_B + c * BX_LEN + ((j2 & 1) ? BX_3 + (4 * j2 + i0 + 84) * 2 : BX_5 + (4 * j2 + i0 + 80) * 2),
                      sb + CV_SM_B + c * BX_LEN + ((j3 & 1) ? BX_7 : BX_9) + (8 * j3 + i0 + 136) * 2,
                      oc + CV_SM_U + (c * ULEN + UPADF) * 2, sb + CV_SM_U + (c * ULEN + UPADF) * 2 + usw(16 * mat + 2 * r + 2) * 16, oc + CV_SM_Y + c * 8192,
                      sb + CV_SM_T + c * TAPB + TAPE + (307 + 2 * g - ti) * 4, sb + CV_SM_T + c * TAPB + (528 + e) * 4,
                      e == -5 ? 0x4410u : e == -4 ? 0x1044u : 0x4444u, e == 3 ? 0x4410u : e == 4 ? 0x1044u : 0x4444u,
                      c * XCP * 2 + (lane >> 4) * 256 + (lane & 15) * 8};
        asm volatile("st.shared.u32 [%0], %1;" ::"r"(sb + CV_SM_CNT + 120), "r"(l.y ^ l.a4 ^ l.a8 ^ l.uc ^ l.ud ^ l.e4 ^ l.en ^ l.sp ^ l.ss ^ l.go) : "memory");
        return l;
    };
    unsigned char* const dq = reinterpret_cast<unsigned char*>(dst + (size_t)d0 * XCP);
    auto far = [&](auto T0_, const auto& seq, const Lc& lc, int c, int lane, const uint2 (&f)[20], uint32_t kk) {
        constexpr int T0 = T0_, T1 = T0 + 6, TC = T0 > 7 ? T0 : 7, NS = sizeof(seq) / sizeof(seq[0]), PD = T0 > 7 ? CV_PDH : CV_PDF;
        uint32_t bq[28], yw[4], yz[4], P, S;
        uint4 xv, yv;
        asm("prmt.b32 %0, %1, 0, %2;" : "=r"(P) : "r"(kk), "r"(lc.sp));
        asm("prmt.b32 %0, %1, 0, %2;" : "=r"(S) : "r"(kk), "r"(lc.ss));
#pragma unroll
        for (int k = 0; 2 * k < T1 - TC + 4; k++) ldsm_x4(bq + 4 * k, lc.uc + (TC - 8) * 256 + 512 * k);
#pragma unroll
        for (int k = 0; 4 * k < T1 - TC; k++) ldsm_x4(bq + 20 + 4 * k, lc.ud + (TC - 8) * 256 + 1024 * k);
        CST(3);
        mbar_wait(cnt + 8 * c, 0);
        mbar_wait(cnt + 40, 0);
        CST(4);
        float acc[6][4] = {};
        uint32_t a[PD + 1][4];
#pragma unroll
        for (int i = -PD; i < NS + 3; i++) {
            if (i + PD < NS) ldsm_x4_t(a[(i + PD) % (PD + 1)], seq[i + PD] < 32 ? lc.a4 + (seq[i + PD] - 2) * 128 : lc.a8 + (seq[i + PD] - 34) * 256);
            if (i < 0) continue;
#pragma unroll
            for (int T = T0; T < T1; T++) {
                if (i >= NS) break;
                const int ee = seq[i] < 32 ? 2 * T - 6 - seq[i] : T + 35 - seq[i];
                if (i == 0 && T >= TC) mma_bf16(acc[T - T0], P, 0u, S, P, bq[2 * (T - TC)], bq[2 * (T - TC) + 1]);
                if (i == 1 && T >= TC) mma_bf16_k8(acc[T - T0], 0u, S, bq[20 + T - TC]);
                if (i == (T >= TC ? 2 : 0)) mma_bf16(acc[T - T0], f[19].x, 0u, f[19].y, f[19].x, bq[2 * (T - TC + 4)], bq[2 * (T - TC + 4) + 1]);
                if (seq[i] < 32 ? ee >= 0 && ee <= 9 : ee >= 10) mma_bf16(acc[T - T0], a[i % (PD + 1)][0], a[i % (PD + 1)][1], a[i % (PD + 1)][2], a[i % (PD + 1)][3], f[ee].x, f[ee].y);
            }
#pragma unroll
            for (int k = 0; k < 3; k++) {
                const int o = 256 * T0 + 512 * k;
                auto at = [&](int d) { return i - d >= 0 && i - d < NS && seq[i - d < 0 ? 0 : i - d < NS ? i - d : 0] == 2 * T0 + 4 * k - 4; };
                if (at(CV_D2)) {
                    cv_store(dq + lc.go + o, xv, yv);
                    if (layer > 19 - 2 * k) __trap();
                }
                if (at(-2)) { ldsm_x4_t(yw, lc.y + o); ldsm_x4_t(yz, lc.y + 3584 + o); }
                if (at(1)) {
#pragma unroll
                    for (int q = 0; q < 4; q++) yw[q] = add2(add2(yw[q], yz[q]), pack2(acc[2 * k + (q >> 1)][2 * (q & 1)], acc[2 * k + (q >> 1)][2 * (q & 1) + 1]));
                    stsm_x4_t(lc.y + o, yw[0], yw[1], yw[2], yw[3]);
                    xv = ldx(smem_u32(Xs) + lc.go + o);
                    __syncwarp();
                    yv = lds4(smem_u32(sm + CV_SM_Y) + c * 8192 + o + usw(lane) * 16);
                    if (layer > 20 - 2 * k) __trap();
                    if (k == 2) CST(6);
                }
            }
        }
    };
    TSTAMP1X(9, 256);
    if (threadIdx.x >= 256) {
        if (threadIdx.x < 288 && elect()) {
            mbar_init(cnt + 48, 1);
            asm volatile("fence.mbarrier_init.release.cluster;" ::: "memory");
            bulk_load(smem_u32(sm + CV_SM_T), tap + d0 * (TAPB / 16), CV_CPB * TAPB, cnt + 48);
            mbar_expect_tx(cnt + 48, CV_CPB * TAPB);
        }
        CV_IDX
        const int wgu = (warp >> 2) & 1, g = lane >> 2, ti = lane & 3;
        CST(1);
        if (warp > 8 && elect()) {
            if (warp < 15) mbar_init(cnt + 8 * (warp - 9), warp == 14 ? 8 : 4);
            else if (layer) prefetch_tmap(&tmOut);
        }
        if (warp < 13 && lane < 17 - (warp == 12)) {
            const int off = warp == 12 ? CV_SM_U : CV_SM_B + (warp == 11 ? BX_7 : (warp - 8) * BX_3), str = warp == 12 ? ULEN * 2 : BX_LEN;
#pragma unroll
            for (int c = 0; c < CV_CPB; c++) *reinterpret_cast<uint4*>(sm + off + c * str + 16 * lane) = make_uint4(0, 0, 0, 0);
        }
        fence_async_smem();
        asm volatile("bar.arrive 3, 512;" ::: "memory");
        asm volatile("bar.sync 1, 256;" ::: "memory");
        TSTAMP1X(10, 256);
        asm volatile("setmaxnreg.inc.sync.aligned.u32 168;");
        const uint32_t Tc = smem_u32(sm + CV_SM_T) + (16 + 128 * (warp & 2) + 8 * (warp & 1) + g - 2 * ti) * 4;
        uint2 fa[8][2], fn[8][2];
        auto near_taps = [&](uint2 (&f)[8][2], int c) {
#pragma unroll
            for (int m = 0; m < 16; m++) f[m >> 1][m & 1] = make_uint2(lds1v(Tc + c * TAPB + 64 * (m >> 1) - 32 * (m & 1)), lds1v(Tc + c * TAPB + 64 * (m >> 1) - 32 * (m & 1) + 512));
        };
        CST(6);
        mbar_wait(cnt + 48, 0);
        TSTAMP1X(11, 256); CST(5);
        near_taps(fa, 3 * wgu);
        near_taps(fn, 2 - wgu);
        const int hc = wgu ? warp & 3 : 4;
        const Lc lc = lane_consts(lane, hc);
        TSTAMP1X(12, 256); CST(0);
        uint32_t ya = smem_u32(sm + CV_SM_Y) + wgu * 8192 + (warp & 2) * 2048 + usw(2 * lane + (warp & 1)) * 16;
        uint64_t db = make_desc(smem_u32(Us + wgu * ULEN + UPADF), 16, 256, 3);
        if (wgu) { asm volatile("bar.sync 6, 384;" ::: "memory"); fence_async_smem(); }
        int c = wgu;
        auto chain = [&](const uint2 (&f)[8][2], auto&& meanwhile) {
            float acc[64];
            asm volatile("bar.sync %0, %1;" ::"r"(c ? 4 + wgu : 2), "r"(c ? 256 : 384) : "memory");
            TSTAMPC(1 + 3 * c);
            if (c < 2) CST(7);
            if (c == 0) fence_async_smem();
            wgmma_fence();
#pragma unroll
            for (int m = 0; m < 8; m++) {
                wgmma_rs128(acc, f[m][0], f[m][1], db - (uint64_t)(2 * m), m);
                if (m == CV_HAND && c < 4) asm volatile("bar.arrive %0, 256;" ::"r"(5 - wgu) : "memory");
            }
            wgmma_commit();
            asm volatile("griddepcontrol.launch_dependents;" ::: "memory");
            TSTAMPC(2 + 3 * c); CST(13 + (c >> 1));
            meanwhile();
            wgmma_wait<0>();
            TSTAMPC(3 + 3 * c); CST(10 + (c >> 1));
            uint32_t w[16];
#pragma unroll
            for (int j = 0; j < 16; j++) w[j] = j ? pack2(acc[4 * j] + acc[4 * j - 2], acc[4 * j + 1] + acc[4 * j - 1]) : pack2(acc[0], acc[1]);
#pragma unroll
            for (int j = 0; j < 16; j += 4) stsm_x4_t(ya + 256 * j, w[j], w[j + 1], w[j + 2], w[j + 3]);
            __syncwarp();
            if (lane == 0) mbar_arrive(cnt + 8 * c);
            c += 2; ya += 16384; db += ULEN / 4;
        };
        const uint32_t e4 = lc.e4, e8 = e4 + 428 - 4 * g;
        uint2 fl[4];
        uint32_t kk;
#pragma unroll 1
        for (;;) {
            if (c != 1) chain(fa, [&] {
                if (c == 3 || warp + c == 12) {
#pragma unroll
                    for (int k = 0; k < 19; k++) (k < 16 ? fn[(k >> 1) & 7][k & 1] : fl[k & 3]) = make_uint2(lds1(k < 10 ? e4 + 32 * k + 16 : e8 + 32 * k - 304), lds1(k < 10 ? e4 + 32 * k : e8 + 32 * k - 320));
                    fl[3] = make_uint2(lds1(lc.en), lds1(lc.en - 32));
                    kk = lds1(smem_u32(sm + CV_SM_T) + TAPB * hc + TAPE + 1672);
                }
            });
            if (c > 4) break;
            if (c == 2) { asm volatile("bar.sync 7, 384;" ::: "memory"); fence_async_smem(); }
            chain(fn, [&] { if (c == 2) near_taps(fa, 4); });
        }
        TSTAMP1X(6, 256); CST(2);
        if (wgu || warp == 8) {
            constexpr int seq[29] = {5, 6, 32, 7, 33, 8, 34, 9, 35, 10, 36, 11, 12, 13, 14, 15, 16, 17, 37, 18, 38, 19, 20, 21, 39, 22, 40, 23, 24};
            uint2 f[20];
#pragma unroll
            for (int k = 0; k < 20; k++) f[k] = k < 16 ? fn[(k >> 1) & 7][k & 1] : fl[k & 3];
            far(Int<10>(), seq, lc, hc, lane, f, kk);
        }
    } else {
        asm volatile("setmaxnreg.dec.sync.aligned.u32 88;");
        CV_IDX
        CST(5);
        const uint4* ppv = piv + tid;
        const float4* psv = sum + tid;
        const uint2* pxv = reinterpret_cast<const uint2*>(x1T + (size_t)d0 * XCP) + (tid >> 4) * 32 + (tid & 15);
        asm volatile("st.shared.u64 [%0], %1;" ::"r"(smem_u32(sm + CV_SM_O) + tid * 16), "l"((uint64_t)ppv ^ (uint64_t)psv ^ (uint64_t)pxv) : "memory");
        const int tc = (0x04302100 >> (4 * warp)) & 7;
        const Lc lc = lane_consts(lane, tc);
        pdl_sync();
        SPAN(3 + 4 * layer, 1);
        TSTAMP(0); CST(0);
        if (tid == 0) TSTAMPC(0);
        if (threadIdx.x == 0) { GSTAMP(g_tim, 15); }
        float4 sv[4];
        uint4 pv;
#pragma unroll
        for (int k = 0; k < 4; k++)
            asm volatile(CV_LD ".v4.f32 {%0,%1,%2,%3}, [%4];" : "=f"(sv[k].x), "=f"(sv[k].y), "=f"(sv[k].z), "=f"(sv[k].w) : "l"(psv + 256 * k) : "memory");
        asm volatile(CV_LD ".v4.u32 {%0,%1,%2,%3}, [%4];" : "=r"(pv.x), "=r"(pv.y), "=r"(pv.z), "=r"(pv.w) : "l"(ppv) : "memory");
        uint2 xe[CV_CPB], xo[CV_CPB];
#pragma unroll
        for (int c = 0; c < CV_NL; c++) {
            asm volatile(CV_LD ".v2.u32 {%0,%1}, [%2];" : "=r"(xe[c].x), "=r"(xe[c].y) : "l"(pxv + c * (XCP / 4)) : "memory");
            asm volatile(CV_LD ".v2.u32 {%0,%1}, [%2];" : "=r"(xo[c].x), "=r"(xo[c].y) : "l"(pxv + c * (XCP / 4) + 16) : "memory");
        }
#define CV_XD 300
#define CV_XW 0
        if (warp == CV_XW) {
            if (elect()) {
                const uint32_t c0 = clock();
                mbar_init(cnt + 56, 1);
                asm volatile("fence.mbarrier_init.release.cluster;" ::: "memory");
                mbar_expect_tx(cnt + 56, CV_CPB * 4096);
                while (clock() - c0 < CV_XD) ;
#pragma unroll
                for (int c = CV_NL; c < CV_CPB + CV_NL; c++) bulk_load(smem_u32(Xs + (c % CV_CPB) * XLEN), x1T + (size_t)(d0 + c % CV_CPB) * XCP, 4096, cnt + 56);
            }
            __syncwarp();
            CST(15);
        }
        constexpr float idm = 1.0f / DM;
        uint32_t mw[4];
        float rs[8];
#pragma unroll
        for (int k = 0; k < 4; k++) {
            const uint32_t pw = k == 0 ? pv.x : k == 1 ? pv.y : k == 2 ? pv.z : pv.w;
            mw[k] = pack2(fmaf(sv[k].x, idm, __uint_as_float(pw << 16)), fmaf(sv[k].z, idm, __uint_as_float(pw & 0xffff0000u)));
            uint32_t vr;
            asm("cvt.rn.relu.bf16x2.f32 %0, %1, %2;" : "=r"(vr) : "f"(fmaf(sv[k].z * -idm, sv[k].z, sv[k].w) * idm), "f"(fmaf(sv[k].x * -idm, sv[k].x, sv[k].y) * idm));
            const uint32_t ve = pack2(__uint_as_float(vr << 16) + 1e-5f, __uint_as_float(vr & 0xffff0000u) + 1e-5f);
            const uint32_t sd = pack2(sqrt_apx(__uint_as_float(ve << 16)), sqrt_apx(__uint_as_float(ve & 0xffff0000u)));
            rs[2 * k] = rcp_apx(__uint_as_float(sd << 16)); rs[2 * k + 1] = rcp_apx(__uint_as_float(sd & 0xffff0000u));
        }
        if (rs[0] != 123.f) TSTAMP(13);
        const uint32_t ua = smem_u32(Us) + usw(tid + UPADF / 8) * 16;
        uint32_t uw[CV_CPB][4];
#pragma unroll
        for (int c = 0; c < CV_CPB; c++) {
            if (c == CV_NL) {
                if (warp == CV_XW) { mbar_wait(cnt + 56, 0); CST(7); }
                asm volatile("bar.sync 10, 256;" ::: "memory");
            }
            if (c == 1 || c == 2) {
#pragma unroll
                for (int k = c; k < (c == 1 ? 2 : CV_CPB); k++) {
 const uint4 v = ldx(smem_u32(Xs + k * XLEN) + (tid >> 4) * 256 + (tid & 15) * 8); xe[k] = make_uint2(v.x, v.y); xo[k] = make_uint2(v.z, v.w); }
            }
            const uint32_t e0 = sub2(xe[c].x, mw[0]), e1 = sub2(xe[c].y, mw[1]), o0 = sub2(xo[c].x, mw[2]), o1 = sub2(xo[c].y, mw[3]);
            uw[c][0] = pack2(__uint_as_float(e0 << 16) * rs[0], __uint_as_float(o0 << 16) * rs[4]); uw[c][1] = pack2(__uint_as_float(e0 & 0xffff0000u) * rs[1], __uint_as_float(o0 & 0xffff0000u) * rs[5]);
            uw[c][2] = pack2(__uint_as_float(e1 << 16) * rs[2], __uint_as_float(o1 << 16) * rs[6]); uw[c][3] = pack2(__uint_as_float(e1 & 0xffff0000u) * rs[3], __uint_as_float(o1 & 0xffff0000u) * rs[7]);
            asm volatile("st.shared.v4.u32 [%0], {%1,%2,%3,%4};" ::"r"(ua + c * ULEN * 2), "r"(uw[c][0]), "r"(uw[c][1]), "r"(uw[c][2]), "r"(uw[c][3]) : "memory");
            if (c < 2) {
                asm volatile("bar.arrive %0, 384;" ::"r"(2 + 4 * c) : "memory");
                if (layer > 29 - c) __trap();
                CST(11 + c);
            }
        }
        asm volatile("bar.arrive 7, 384;" ::: "memory");
        asm volatile("bar.sync 3, 512;" ::: "memory");
        TSTAMP(1); CST(1);
        {
            auto box = [&](auto c0, auto c1, int chunk, int cb, bool full) {
                const uint32_t ea = smem_u32(Us + cb * ULEN) + usw(chunk + UPADF / 8 + (lane ? 1 : -1)) * 16, bx = smem_u32(sm + CV_SM_B + cb * BX_LEN) + chunk * 16;
                uint32_t lo[CV_CPB][4], hi[CV_CPB][2];
#pragma unroll
                for (int c = c0; c < c1; c++) {
                    lo[c][0] = 0;
#pragma unroll
                    for (int k = 1; k < 4; k++) lo[c][k] = __shfl_up_sync(~0u, uw[c][k], 1);
#pragma unroll
                    for (int k = 0; k < 2; k++) hi[c][k] = __shfl_down_sync(~0u, uw[c][k], 1);
                }
#pragma unroll
                for (int c = c0; c < c1; c++)
                    asm volatile("{\n.reg .pred p, q;\nsetp.eq.s32 p, %7, 0;\nsetp.eq.s32 q, %7, 31;\n@p ld.shared.v4.u32 {%0,%1,%2,%3}, [%6];\n@q ld.shared.v2.u32 {%4,%5}, [%6];\n}"
                                 : "+r"(lo[c][0]), "+r"(lo[c][1]), "+r"(lo[c][2]), "+r"(lo[c][3]), "+r"(hi[c][0]), "+r"(hi[c][1]) : "r"(ea + c * ULEN * 2), "r"(lane) : "memory");
#pragma unroll
                for (int c = c0; c < c1; c++) {
                    const uint32_t e[9] = {lo[c][1], lo[c][2], lo[c][3], uw[c][0], uw[c][1], uw[c][2], uw[c][3], hi[c][0], hi[c][1]};
                    uint32_t o[8], p[8], t[7], b3[5], b5[7];
#pragma unroll
                    for (int i = 0; i < 8; i++) { o[i] = __byte_perm(e[i], e[i + 1], 0x5432); p[i] = add2(e[i], o[i]); }
#pragma unroll
                    for (int i = 0; i < 5; i++) b3[i] = add2(o[i], p[i + 1]);
                    sts4(bx + c * BX_LEN + BX_3 + 160, b3);
#pragma unroll
                    for (int i = 1; i < 7; i++) { t[i] = add2(p[i], p[i + 1]); b5[i] = add2(t[i], e[i + 2]); }
                    sts4(bx + c * BX_LEN + BX_5 + 160, b5 + 2);
                    if (full) {
#pragma unroll
                        for (int i = 1; i < 5; i++) { b3[i] = add2(b3[i], t[i + 2]); t[i] = add2(t[i], b5[i + 2]); }
                        sts4(bx + c * BX_LEN + BX_7 + 272, b3 + 1);
                        sts4(bx + c * BX_LEN + BX_9 + 272, t + 1);
                    }
                }
            };
            auto reload = [&](int c, uint32_t a) { const uint4 v = lds4(a); uw[c][0] = v.x; uw[c][1] = v.y; uw[c][2] = v.z; uw[c][3] = v.w; };
            if (warp >= 6) {
#pragma unroll
                for (int c = 0; c < 3; c++) reload(c, ua - 1024 + (c + 2) * ULEN * 2);
            }
            if (warp >= 4) {
#pragma unroll
                for (int c = 3; c < 5; c++) reload(c, ua - 2048 + c * ULEN * 2);
            }
            box(Int<0>(), Int<3>(), warp < 6 ? tid : tid - 64, warp < 6 ? 0 : 2, warp < 4);
            if (warp >= 4) box(Int<3>(), Int<5>(), tid - 128, 0, true);
            else if (tid >= 128 - CV_CPB) {
                const int c = 127 - tid;
                const uint2 v = *reinterpret_cast<const uint2*>(Us + c * ULEN + UPADF);
                const float s1 = __uint_as_float(v.x << 16), s2 = s1 + __uint_as_float(v.x & 0xffff0000u), s3 = s2 + __uint_as_float(v.y << 16), s4 = s3 + __uint_as_float(v.y & 0xffff0000u);
                unsigned char* bc = sm + CV_SM_B + c * BX_LEN;
                *reinterpret_cast<uint32_t*>(bc + BX_5 + 156) = pack2(s1, s2);
                *reinterpret_cast<uint2*>(bc + BX_7 + 264) = make_uint2(v.x << 16, pack2(s2, s3));
                *reinterpret_cast<uint2*>(bc + BX_9 + 264) = make_uint2(pack2(s1, s2), pack2(s3, s4));
            }
        }
        __syncwarp();
        if (lane == 0) mbar_arrive(cnt + 40);
        TSTAMP(2); CST(2);
        if (layer && blockIdx.x == 0 && tid == 224) g_epoch = ld_epoch();
        __syncwarp();
        if ((0x6e >> warp) & 1) {
            constexpr int seq[16] = {0, 1, 2, 3, 4, 5, 6, 32, 7, 8, 9, 33, 10, 34, 11, 12};
            uint2 f[20];
            mbar_wait(cnt, 0);
            const uint32_t e8 = lc.e4 + 428 - (lane & 28);
#pragma unroll
            for (int k = 0; k < 13; k++) f[k] = make_uint2(lds1(k < 10 ? lc.e4 + 32 * k + 16 : e8 + 32 * k - 304), lds1(k < 10 ? lc.e4 + 32 * k : e8 + 32 * k - 320));
            f[19] = make_uint2(lds1(lc.en), lds1(lc.en - 32));
            far(Int<4>(), seq, lc, tc, lane, f, lds1(smem_u32(sm + CV_SM_T) + TAPB * tc + TAPE + 1672));
        }
    }
    {
        CV_IDX
        if ((0xc91 >> warp) & 1) {
            const int c = __popc(0xc91 & ((1 << warp) - 1));
            uint4 xv[2], yv[2];
#pragma unroll
            for (int k = 0; k < 2; k++) xv[k] = ldx(smem_u32(Xs + c * XLEN) + 512 * k + (lane >> 4) * 256 + (lane & 15) * 8);
            const uint32_t u0 = lds1(smem_u32(Us + c * ULEN) + (lane == 31 ? UPADF * 2 : 0));
            mbar_wait(cnt + 8 * c, 0);
#pragma unroll
            for (int k = 0; k < 2; k++) yv[k] = lds4(smem_u32(sm + CV_SM_Y) + c * 8192 + 512 * k + usw(lane) * 16);
            const uint4 yz = lds4(smem_u32(sm + CV_SM_Y) + c * 8192 + 4096 + usw(lane) * 16);
            const float kk = __uint_as_float(lds1(smem_u32(sm + CV_SM_T) + TAPB * c + TAPE + 1272) << 16);
            yv[1].x = add2(yv[1].x, yz.x); yv[1].y = add2(yv[1].y, yz.y); yv[1].z = add2(yv[1].z, yz.z);
            yv[1].w = pack2(fmaf(kk, __uint_as_float(u0 << 16), __uint_as_float(yv[1].w << 16) + __uint_as_float(yz.w << 16)),
                            fmaf(kk, __uint_as_float(u0 << 16) + __uint_as_float(u0 & 0xffff0000u), __uint_as_float(yv[1].w & 0xffff0000u) + __uint_as_float(yz.w & 0xffff0000u)));
#pragma unroll
            for (int k = 0; k < 2; k++) cv_store(dq + c * XCP * 2 + (lane >> 4) * 256 + (lane & 15) * 8 + 512 * k, xv[k], yv[k]);
        }
        TSTAMP(4); CST(8);
        if (layer == 1) {
            const int rb = (blockIdx.x >> 3) + (warp & 8) * 2, cg = blockIdx.x & 7, ch = (tid >> 3) & 31;
            const bf16* src = dst + (size_t)(cg * 80 + ch) * XCP + rb * 64 + (tid & 7) * 8;
            uint32_t v[3][4];
            __syncthreads();
            if (warp & 8) { const uint32_t c0 = clock(); while (clock() - c0 < 300) ; }
            uint32_t todo = (warp & 4) ? 3 : 7;
#pragma unroll 1
            for (int it = 0; it < SPIN_MAX; it++) {
#pragma unroll
                for (int k = 0; k < 3; k++)
                    if (todo >> k & 1)
                        asm volatile("ld.relaxed.gpu.global.v4.u32 {%0,%1,%2,%3}, [%4];" : "=r"(v[k][0]), "=r"(v[k][1]), "=r"(v[k][2]), "=r"(v[k][3]) : "l"(src + k * (32 * XCP)) : "memory");
#pragma unroll
                for (int k = 0; k < 3; k++)
                    if ((todo >> k & 1) && v[k][0] != ~0u && v[k][1] != ~0u && v[k][2] != ~0u && v[k][3] != ~0u) {
                        *reinterpret_cast<uint4*>(sm + (32 * k + ch) * 272 + ((tid & 7) + (warp & 8)) * 16) = make_uint4(v[k][0], v[k][1], v[k][2], v[k][3]);
                        todo ^= 1u << k;
                    }
                if (!todo) break;
                __nanosleep(CV_SLEEP);
            }
            __syncwarp();
            asm volatile("bar.sync %0, 256;" ::"r"(8 + (warp >> 3)) : "memory");
            uint32_t w[12];
#pragma unroll
            for (int k = 0; k < 3; k++) ldsm_x4(&w[4 * k], smem_u32(sm) + min(32 * k + lane, 79) * 272 + warp * 16);
            const uint32_t ot = smem_u32(sm + CV_SM_O) + warp * 1280, oa = ot + (lane & 7) * 160 + (lane >> 3) * 16;
            stsm_x4_t(oa, w[0], w[1], w[2], w[3]);
            stsm_x4_t(oa + 64, w[4], w[5], w[6], w[7]);
            asm volatile("stmatrix.sync.aligned.m8n8.x2.trans.shared.b16 [%0], {%1,%2};" ::"r"(oa + 128), "r"(w[8]), "r"(w[9]) : "memory");
            fence_async_smem();
            __syncwarp();
            if (lane == 0) {
                asm volatile("cp.async.bulk.tensor.3d.global.shared::cta.bulk_group [%0, {%1, %2, %3}], [%4];" ::"l"(&tmOut), "r"(cg * 80), "r"((rb >> 1) * 64 + 8 * (warp & 7)), "r"(rb & 1), "r"(ot) : "memory");
                asm volatile("cp.async.bulk.commit_group;" ::: "memory");
                asm volatile("cp.async.bulk.wait_group.read 0;" ::: "memory");
            }
        }
    }
    TSTAMP(3); CST(9); CST_END;
    GSTAMP(g_tim, 14);
    SPAN(3 + 4 * layer, 3);
}

template <int TA, int TB>
__device__ __forceinline__ void wgmma_n240(float (&d)[120], uint64_t da, uint64_t db, int acc) {
    asm volatile("{\n.reg .pred p;\nsetp.ne.b32 p, %124, 0;\nwgmma.mma_async.sync.aligned.m64n240k16.f32.bf16.bf16 {%0,%1,%2,%3,%4,%5,%6,%7,%8,%9,%10,%11,%12,%13,%14,%15,%16,%17,%18,%19,%20,%21,%22,%23,%24,%25,%26,%27,%28,%29,%30,%31,%32,%33,%34,%35,%36,%37,%38,%39,%40,%41,%42,%43,%44,%45,%46,%47,%48,%49,%50,%51,%52,%53,%54,%55,%56,%57,%58,%59,%60,%61,%62,%63,%64,%65,%66,%67,%68,%69,%70,%71,%72,%73,%74,%75,%76,%77,%78,%79,%80,%81,%82,%83,%84,%85,%86,%87,%88,%89,%90,%91,%92,%93,%94,%95,%96,%97,%98,%99,%100,%101,%102,%103,%104,%105,%106,%107,%108,%109,%110,%111,%112,%113,%114,%115,%116,%117,%118,%119}, %120, %121, p, 1, 1, %122, %123;\n}"
                 : "+f"(d[0]), "+f"(d[1]), "+f"(d[2]), "+f"(d[3]), "+f"(d[4]), "+f"(d[5]), "+f"(d[6]), "+f"(d[7]), "+f"(d[8]), "+f"(d[9]), "+f"(d[10]), "+f"(d[11]), "+f"(d[12]), "+f"(d[13]), "+f"(d[14]), "+f"(d[15]), "+f"(d[16]), "+f"(d[17]), "+f"(d[18]), "+f"(d[19]), "+f"(d[20]), "+f"(d[21]), "+f"(d[22]), "+f"(d[23]), "+f"(d[24]), "+f"(d[25]), "+f"(d[26]), "+f"(d[27]), "+f"(d[28]), "+f"(d[29]), "+f"(d[30]), "+f"(d[31]), "+f"(d[32]), "+f"(d[33]), "+f"(d[34]), "+f"(d[35]), "+f"(d[36]), "+f"(d[37]), "+f"(d[38]), "+f"(d[39]), "+f"(d[40]), "+f"(d[41]), "+f"(d[42]), "+f"(d[43]), "+f"(d[44]), "+f"(d[45]), "+f"(d[46]), "+f"(d[47]), "+f"(d[48]), "+f"(d[49]), "+f"(d[50]), "+f"(d[51]), "+f"(d[52]), "+f"(d[53]), "+f"(d[54]), "+f"(d[55]), "+f"(d[56]), "+f"(d[57]), "+f"(d[58]), "+f"(d[59]), "+f"(d[60]), "+f"(d[61]), "+f"(d[62]), "+f"(d[63]), "+f"(d[64]), "+f"(d[65]), "+f"(d[66]), "+f"(d[67]), "+f"(d[68]), "+f"(d[69]), "+f"(d[70]), "+f"(d[71]), "+f"(d[72]), "+f"(d[73]), "+f"(d[74]), "+f"(d[75]), "+f"(d[76]), "+f"(d[77]), "+f"(d[78]), "+f"(d[79]), "+f"(d[80]), "+f"(d[81]), "+f"(d[82]), "+f"(d[83]), "+f"(d[84]), "+f"(d[85]), "+f"(d[86]), "+f"(d[87]), "+f"(d[88]), "+f"(d[89]), "+f"(d[90]), "+f"(d[91]), "+f"(d[92]), "+f"(d[93]), "+f"(d[94]), "+f"(d[95]), "+f"(d[96]), "+f"(d[97]), "+f"(d[98]), "+f"(d[99]), "+f"(d[100]), "+f"(d[101]), "+f"(d[102]), "+f"(d[103]), "+f"(d[104]), "+f"(d[105]), "+f"(d[106]), "+f"(d[107]), "+f"(d[108]), "+f"(d[109]), "+f"(d[110]), "+f"(d[111]), "+f"(d[112]), "+f"(d[113]), "+f"(d[114]), "+f"(d[115]), "+f"(d[116]), "+f"(d[117]), "+f"(d[118]), "+f"(d[119])
                 : "l"(da), "l"(db), "n"(TA), "n"(TB), "r"(acc));
}

__device__ __forceinline__ void wgmma_n80(float (&d)[40], uint64_t da, uint64_t db, int acc) {
    asm volatile("{\n.reg .pred p;\nsetp.ne.b32 p, %42, 0;\nwgmma.mma_async.sync.aligned.m64n80k16.f32.bf16.bf16 {%0,%1,%2,%3,%4,%5,%6,%7,%8,%9,%10,%11,%12,%13,%14,%15,%16,%17,%18,%19,%20,%21,%22,%23,%24,%25,%26,%27,%28,%29,%30,%31,%32,%33,%34,%35,%36,%37,%38,%39}, %40, %41, p, 1, 1, 0, 1;\n}"
                 : "+f"(d[0]), "+f"(d[1]), "+f"(d[2]), "+f"(d[3]), "+f"(d[4]), "+f"(d[5]), "+f"(d[6]), "+f"(d[7]), "+f"(d[8]), "+f"(d[9]), "+f"(d[10]), "+f"(d[11]), "+f"(d[12]), "+f"(d[13]), "+f"(d[14]), "+f"(d[15]), "+f"(d[16]), "+f"(d[17]), "+f"(d[18]), "+f"(d[19]), "+f"(d[20]), "+f"(d[21]), "+f"(d[22]), "+f"(d[23]), "+f"(d[24]), "+f"(d[25]), "+f"(d[26]), "+f"(d[27]), "+f"(d[28]), "+f"(d[29]), "+f"(d[30]), "+f"(d[31]), "+f"(d[32]), "+f"(d[33]), "+f"(d[34]), "+f"(d[35]), "+f"(d[36]), "+f"(d[37]), "+f"(d[38]), "+f"(d[39])
                 : "l"(da), "l"(db), "r"(acc));
}

constexpr int A1_THREADS = 384;
constexpr int A1_NST = 4;
#define A1_SKEW 8
constexpr int A1_STAGE = 16384 + WQ_STAGE;
constexpr int A1_KVP = 336;
constexpr int A1_SM_KV = 2 * A1_STAGE;
constexpr int A1_SM_END = A1_NST * A1_STAGE;
constexpr int A1_SM_BAR = A1_SM_END + 3072 + 3 * WOB + 64;
constexpr int A1_SM_RS = A1_SM_END + 512;
constexpr int A1_SM_W0 = A1_SM_END + 3072, A1_SM_W3 = A1_SM_END - 3 * WOB, A1_SM_A1 = 2 * WOB, A1_SM_A0 = A1_SM_A1 + 61440;
constexpr int A1_SM_XA = A1_SM_W0 + 2 * WOB, A1_SM_XB = A1_SM_XA + 2048;
constexpr int A1_SMEM = A1_SM_BAR + 512 + 7 * CST_EXTRA / 4;
static_assert(A1_SM_W3 >= A1_SM_KV + 144 * A1_KVP && A1_SM_W3 % 512 == 0 && A1_SM_A1 % 1024 == 0 && A1_SM_A0 <= A1_SM_KV && A1_SM_A0 + 61440 <= A1_SM_W3 && A1_SMEM <= 232448 && 11 * 4096 <= A1_STAGE, "layout");
__device__ __forceinline__ constexpr uint32_t wo_off(int h) { return h * WOB + (h < 3 ? A1_SM_W0 : h < 6 ? A1_SM_W3 - 3 * WOB : -6 * WOB); }
#define A1_FRED "red.relaxed.gpu.global.add.u32"
#define A1_FLD "ld.relaxed.gpu.global.u32"
#define ST_SLEEP 20
#define ST_SLEEP0 300
#define A1_P0 2
#define A1_PW (kb - 2)
#define A1_FSPIN SPIN_MAX
#define A1_FSLEEP 40
#define YT_LAYER 1
#define WOT 11
#define A1_WOAT 6

template <int L>
__device__ __forceinline__ void a1_mainloop(float (&acc)[120], uint32_t sbase, uint32_t bars, int wg, int tile) {
    constexpr int layer = L; (void)layer;
    const uint64_t da0 = L ? make_desc(sbase + wg * 8192, 8192, 1024, 1) : make_desc(sbase + wg * 8192, 16, 1024, 1), db0 = make_desc(sbase + 16384, 1024, 256, 3);
#pragma unroll 1
    for (int t = 0;; t++) {
        const int st = t % A1_NST;
        mbar_wait(bars + 8 * st, (t / A1_NST) & 1);
        if (t == A1_SKEW && wg == 0) mbar_wait(bars + 160, 0);
        TSTAMP3(1 + t);
        if (t == 0) CSA(0);
        wgmma_fence();
#pragma unroll
        for (int kk = 0; kk < 4; kk++) wgmma_n240<L, 1>(acc, da0 + (uint32_t)(st * (A1_STAGE / 16) + kk * (L ? 128 : 2)), db0 + (uint32_t)(st * (A1_STAGE / 16) + (kk >> 1) * (WQ_STAGE / 32) + (kk & 1) * 32), kk ? 1 : t);
        wgmma_commit();
        if (t == 9) break;
        if (t == A1_SKEW - 1 && wg == 0) wgmma_wait<0>(); else wgmma_wait<1>();
        if (t > 0 && (threadIdx.x & 127) == 0) {
            if (t != A1_SKEW || wg) mbar_arrive(bars + 8 * (A1_NST + (t - 1) % A1_NST));
            if (t == A1_SKEW - 1 && wg == 0) mbar_arrive(bars + 8 * (A1_NST + t % A1_NST));
        }
    }
}

template <bool MAP>
__global__ void __launch_bounds__(A1_THREADS, 1) a1_kernel(const __grid_constant__ Par in, const __grid_constant__ CUtensorMap tmX, const __grid_constant__ CUtensorMap tmR,
                                                           const __grid_constant__ CUtensorMap tmX1, const __grid_constant__ KgMaps tmW, const __grid_constant__ TileTab tab) {
#define layer in.layer
    const unsigned char* const wo = reinterpret_cast<const unsigned char*>(in.wop);
    float2* const rsum = reinterpret_cast<float2*>(in.sum);
    uint4* const of = in.of;
    extern __shared__ __align__(1024) unsigned char stg[];
    const uint32_t sbase = smem_u32(stg);
    const uint32_t bars = sbase + A1_SM_BAR;
    const uint32_t bar_stat = bars + 64, bar_kv = bars + 72, bar_rd = bars + 168;
    const uint32_t bar_wo = bars + 208, bar_done = bars + 216, bar_pv = bars + 224, bar_kvf = bars + 232, bar_f2 = bars + 248, bar_e2 = bars + 384, que = bars + 448;
    const int tid = threadIdx.x;
    CSK(0);
    const int w = __shfl_sync(~0u, tid >> 5, 0), wg = w >> 2;
    uint32_t smid;
    asm volatile("mov.u32 %0, %smid;" : "=r"(smid));
    const uint4 tv = tab.e[(MAP ? smid : blockIdx.x) + (tid & (smid >> 12))];
    const uint64_t pa = reinterpret_cast<const uint64_t*>(&in)[tid & (smid >> 12)], pb = reinterpret_cast<const uint64_t*>(&in)[6 + (tid & (smid >> 12))];
    const bool one = elect();
    uint32_t tz;
    const unsigned char* wq;
    auto entry = [&] { tz = __shfl_sync(~0u, tv.z, 0); wq = (const unsigned char*)(((uint64_t)__shfl_sync(~0u, tv.y, 0) << 32) | __shfl_sync(~0u, tv.x, 0)); };
    auto issue_w = [&](unsigned it) { bulk_load(sbase + (it % A1_NST) * A1_STAGE + 16384, wq + it * WQ_STAGE, WQ_STAGE, bars + 8 * (it % A1_NST)); };
    auto issue_x = [&](unsigned it, int kb) {
        asm volatile("cp.async.bulk.tensor.5d.shared::cluster.global.mbarrier::complete_tx::bytes [%0], [%1, {%3, %3, %3, %4, %5}], [%2];"
                     ::"r"(sbase + (it % A1_NST) * A1_STAGE), "l"(&tmX), "r"(bars + 8 * (it % A1_NST)), "r"(0), "r"(tz & 15), "r"(kb) : "memory");
    };
    auto first_x = [&] {
        issue_x(0, (tz >> 16) & 7); issue_x(1, ((tz >> 16) & 7) + 1);
    };
    auto expect = [&] {
#pragma unroll
        for (int i = 0; i < A1_NST; i++) mbar_expect_tx(bars + 8 * i, A1_STAGE);
    };
    if (w == 8) {
        if (one) {
            prefetch_tmap(&tmX); prefetch_tmap(&tmW.q);
#pragma unroll
            for (int i = 0; i < A1_NST; i++) mbar_init(bars + 8 * i, 1);
            asm volatile("fence.mbarrier_init.release.cluster;" ::: "memory");
        }
        __syncwarp();
        asm volatile("bar.arrive 0, 384;" ::: "memory");
        if (smid >> 12) __trap();
        entry();
        if ((tz & 0x80000010u) == 16) {
            if (one) {
                issue_w(0);
                asm volatile("griddepcontrol.wait;" ::: "memory");
                first_x();
                issue_w(1);
                expect();
                asm volatile("griddepcontrol.launch_dependents;" ::: "memory");
            }
#pragma unroll
            for (int kb = 2; kb < A1_NST; kb++) {
                __syncwarp();
                mbar_wait(bars + 8 * (kb - 2), 0);
                if (one) { issue_x(kb, ((tz >> 16) & 7) + kb); issue_w(kb); }
                CSK(6 + kb);
            }
        }
        __syncwarp();
        if (!(tz & 16) && blockIdx.x < 128) kgen_first(in, tmW, sbase + A1_SM_W0, bars - 24, one);
        __syncwarp();
    }
    if (w > 8) CSK(8);
    const bool gen = w != 8 && in.logA && blockIdx.x < 128;
    KgPar kp;
    const int w11 = w < 8 ? 2 * (w & 3) + (w >> 2) : w - 1;
    if (gen) kgen_load(in, reinterpret_cast<const bf16*>(pa), w11, kp);
    if (w > 8) CSK(9);
    if (w == 8) {
        const int tile = tz >> 24, mb = tz & 15, hg = (tz >> 8) & 7, kb0 = (tz >> 16) & 7;
        const unsigned l1 = (tz >> 4) & 1;
        if (__builtin_expect(!l1, 0)) {
            CSK(1);
            const uint32_t ep = ld_epoch();
            if (one) {
                kgen_side(in, sbase + A1_SM_W0, bars - 24);
                if (tile < 128) { first_x(); expect(); }
                asm volatile("cp.async.bulk.wait_group 0;" ::: "memory");
            }
            __syncwarp();
            asm volatile("bar.arrive 10, 96;" ::: "memory");
            CSK(6);
            if (tile < 128) {
                await_all(96 + 32 * hg, ep * 15);
                if (one) issue_w(0);
                __syncwarp();
                mbar_wait(bars, 0);
                if (one) { issue_w(1); issue_x(2, kb0 + 2); issue_w(2); }
            }
            CSK(7);
            asm volatile("bar.sync 3, 384;" ::: "memory");
            if (tile < 128 && one) {
                fence_async_smem();
                issue_x(3, kb0 + 3); issue_w(3);
                mbar_expect_tx(bars + 240, 20480);
                bulk_load(sbase + A1_SM_W0, in.x + (size_t)(mb * 128 + hg * 16) * DM, 20480, bars + 240);
            }
            __syncwarp();
            CSK(9);
        } else asm volatile("bar.sync 3, 64;" ::: "memory");
        if (tile < 128 && elect()) {
#pragma unroll 1
            for (unsigned kb = A1_NST; kb < 10; kb++) {
                mbar_wait(bars + 8 * (A1_NST + kb % A1_NST), ((kb / A1_NST) - 1) & 1);
                if (l1 && kb < 9) mbar_wait(bar_rd + 8 * (kb - A1_NST), 0);
                mbar_expect_tx(bars + 8 * (kb % A1_NST), A1_STAGE);
                issue_x(kb, kb < 5 ? kb + kb0 : kb - kb0); issue_w(kb);
                if (kb == (l1 ? A1_WOAT : 9)) {
                    if (!l1) { mbar_wait(bar_stat, 0); asm volatile("fence.proxy.async.global;" ::: "memory"); }
                    mbar_expect_tx(bar_wo, 8 * WOB);
                    bulk_load(sbase + A1_SM_W0, wo + hg * 8 * WOB, 2 * WOB, bar_wo);
                }
            }
            mbar_wait(bars + 8 * (A1_NST + 3), 1);
            bulk_load(sbase + A1_SM_W3, wo + (hg * 8 + 3) * WOB, 3 * WOB, bar_wo);
        }
        CSA(4); CSA_END;
        return;
    }
    {
        if (w < 8 && one) {
#pragma unroll 1
            for (uint32_t c = (w & 4 ? w & 2 ? 0x1111112'01111111ull : 0x1111111'01111184ull : w & 2 ? 0x3122222'01111111ull : 0x1111132'02220000ull) >> (32 * (w & 1)), b = bars + 56 * w; c; c >>= 4, b += 8)
                if (c & 15) mbar_init(b, c & 15);
            asm volatile("fence.mbarrier_init.release.cluster;" ::: "memory");
        }
        __syncwarp();
        asm volatile("bar.sync 0, 384;" ::: "memory");
        if (layer) {
            if (w == 9) asm volatile("bar.arrive 3, 64;" ::: "memory");
        } else {
            if (gen) { SPAN(0, 0); SPAN(0, 1); kgen_tables(in, reinterpret_cast<uint4*>(stg + 3 * A1_STAGE), w11, kp); }
            else if (w != 11 && w11 > 1) asm volatile("bar.arrive 9, 352;" ::: "memory");
            __syncwarp();
            if (w11 < 2) {
                asm volatile("bar.sync 10, 96;" ::: "memory");
                kgen_sums(in, sbase + A1_SM_W0, w11);
                __syncwarp();
                asm volatile("bar.arrive 9, 352;" ::: "memory");
                CSK(1);
            }
            if (w == 9) asm volatile("bar.sync 3, 384;" ::: "memory"); else asm volatile("bar.arrive 3, 384;" ::: "memory");
        }
    }
    tz = __shfl_sync(~0u, tv.z + (uint32_t)(pb >> 32), 0);
    const int tile = tz >> 24, mb = tz & 15, hg = (tz >> 8) & 7;
    float2* rst = reinterpret_cast<float2*>(stg + A1_SM_RS) + 8;
    if (wg == 2) {
        if (w == 11 && layer == 0) {
            asm volatile("bar.sync 9, 352;" ::: "memory");
            CSK(5);
            if (one) publish(64);
            __syncwarp();
            CSK(6);
        }
        if (tile >= 128) { sm_idle(layer); return; }
        if (w == 10) {
            if (one) { prefetch_tmap(&tmR); prefetch_tmap(&tmX1); }
            uint32_t ns;
            asm volatile("mov.u32 %0, %nsmid;" : "=r"(ns));
            if (MAP && ns != 132) __trap();
        }
        __syncwarp();
        if (w == 9) {
            if (layer && one) {
                mbar_expect_tx(bar_stat, 3840);
                bulk_load(sbase + A1_SM_XB, g_xb + tile * 240, 3840, bar_stat);
            }
            __syncwarp();
            uint4* pre = of + (mb * 8 + hg) * 1280 + (tid - 288);
#pragma unroll 1
            for (int k = 0; k < 5 + 5 * layer; k++) {
#pragma unroll
                for (int i = 0; i < 8; i++) asm volatile("st.global.v4.u32 [%0], {%1,%1,%1,%1};" ::"l"(pre + 32 * i), "r"(~0u) : "memory");
                pre += k < 5 ? 256 : XCP / 8;
                if (k == 4) {
                    CSA(2);
                    asm volatile("fence.acq_rel.gpu;" ::: "memory");
                    asm volatile("fence.proxy.async.global;" ::: "memory");
                    __syncwarp();
                    if (tid == 288) mbar_arrive(bar_done);
                    CSA(3);
                    pre = reinterpret_cast<uint4*>(g_yT) + tile * (5 * XCP / 8) + (tid - 288);
                }
            }
            if (layer == 0) {
                asm volatile("griddepcontrol.launch_dependents;" ::: "memory");
                await_all(64, ld_epoch() * gridDim.x);
                CSA(5);
                float4 a[2] = {};
#pragma unroll
                for (int k = 0; k < 10; k++)
#pragma unroll
                    for (int h = 0; h < 2; h++) {
                        const int c4 = min(tid - 288 + 32 * h, 59);
                        const float4 v = __ldcg(reinterpret_cast<const float4*>(g_csp + (k / 5) * 9600 + (k % 5) * 640 + hg * 80) + c4 + (c4 / 20) * 780);
                        a[h].x += v.x; a[h].y += v.y; a[h].z += v.z; a[h].w += v.w;
                    }
#pragma unroll
                for (int h = 0; h < 2; h++)
#pragma unroll
                    for (int k = 0; k < 4; k++) {
                        const float c = 0.5f * (k == 0 ? a[h].x : k == 1 ? a[h].y : k == 2 ? a[h].z : a[h].w), c1 = c - rbf(c), c2 = c1 - rbf(c1);
                        *reinterpret_cast<uint4*>(stg + A1_SM_XB + (4 * min(tid - 288 + 32 * h, 59) + k) * 16) = make_uint4(pack2(c, c1), pack2(c2, 0.f), 0u, 0u);
                    }
                fence_async_smem();
                __syncwarp();
                if (one) {
                    bulk_store(g_xb + tile * 240, sbase + A1_SM_XB, 3840);
                    asm volatile("cp.async.bulk.commit_group;" ::: "memory");
                    asm volatile("cp.async.bulk.wait_group.read 0;" ::: "memory");
                    mbar_arrive(bar_stat);
                }
                __syncwarp();
                CSA(1);
            }
            TSTAMP1T(9, 288);
        } else {
            const int j = tid - 320;
            const uint32_t tag = ld_epoch();
            if (tid == 352) sm_started(layer);
            const int ch = j & 7, kg = (j >> 3) & 3;
            const unsigned char* src = stg + (layer ? (j >> 5) * 8192 + (hg & 3) * 2048 : A1_SM_W0 + (j >> 2) * 1280);
            const int of0 = layer ? kg * 128 + ((ch ^ kg) << 4) : (j & 7) << 4, ofx = layer ? 576 : 64, ofy = layer ? 1024 : 128;
            float s[8], q[8], p0[8];
#pragma unroll
            for (int i = 0; i < 8; i++) { s[i] = 0.f; q[i] = 0.f; }
#pragma unroll 1
            for (int it = 0; it < 5; it++) {
                uint4 v[4];
                mbar_wait(layer ? bars + 8 * (it % A1_NST) : bars + 240, layer * it / A1_NST);
#pragma unroll
                for (int k = 0; k < 4; k++) v[k] = *reinterpret_cast<const uint4*>(src + (layer ? (it % A1_NST) * A1_STAGE : it * 256) + (k & 1 ? of0 ^ ofx : of0) + (k >> 1) * ofy);
                if (it == 0) {
                    const uint4 pv = *reinterpret_cast<const uint4*>(src + (layer ? ch << 4 : 0));
                    const uint32_t w[4] = {pv.x, pv.y, pv.z, pv.w};
#pragma unroll
                    for (int i = 0; i < 4; i++) { p0[2 * i] = __uint_as_float((layer ? w[i] : w[0]) << 16); p0[2 * i + 1] = __uint_as_float(layer ? w[i] & 0xffff0000u : w[0] << 16); }
                }
                asm volatile("" :: "r"(v[0].x), "r"(v[1].x), "r"(v[2].x), "r"(v[3].x), "f"(p0[0]) : "memory");
                __syncwarp();
                if ((tid & 31) == 0) mbar_arrive(bar_rd + 8 * it);
#pragma unroll
                for (int k = 0; k < 4; k++) {
                    const uint32_t w[4] = {v[k].x, v[k].y, v[k].z, v[k].w};
#pragma unroll
                    for (int i = 0; i < 4; i++) {
                        const float a = __uint_as_float(w[i] << 16) - p0[2 * i], b = __uint_as_float(w[i] & 0xffff0000u) - p0[2 * i + 1];
                        s[2 * i] += a; s[2 * i + 1] += b; q[2 * i] = fmaf(a, a, q[2 * i]); q[2 * i + 1] = fmaf(b, b, q[2 * i + 1]);
                    }
                }
            }
            float o[4];
            int row;
            if (layer == 0) {
                float s0 = ((s[0] + s[1]) + (s[2] + s[3])) + ((s[4] + s[5]) + (s[6] + s[7])), q0 = ((q[0] + q[1]) + (q[2] + q[3])) + ((q[4] + q[5]) + (q[6] + q[7]));
#pragma unroll
                for (int o = 1; o <= 2; o <<= 1) { s0 += __shfl_xor_sync(~0u, s0, o); q0 += __shfl_xor_sync(~0u, q0, o); }
                if ((j & 3) == 0) {
                    const float d = s0 * (1.0f / DM);
                    const uint32_t ms = pack2(p0[0] + d, sqrt_apx(rbf(rbf(fmaxf(fmaf(-d, d, q0 * (1.0f / DM)), 0.f)) + 1e-5f)));
                    asm volatile("st.global.cg.u64 [%0], %1;" ::"l"(g_rstat + mb * 128 + (j & 4) * 16 + hg * 8 + (j >> 3)), "l"(tagw(ms, tag)) : "memory");
                    g_piv[mb * 128 + hg * 16 + ((j >> 2) & 8) + (j & 4) + ((j >> 3) & 3)] = __ushort_as_bfloat16((unsigned short)ms);
                }
                ulonglong2 v;
#pragma unroll 1
                for (int it = 0; it < SPIN_MAX; it++) {
                    v = ld_tag2(reinterpret_cast<const ulonglong2*>(g_rstat + mb * 128) + j);
                    if (__all_sync(~0u, tag_ok(v, tag))) break;
                    __nanosleep(100);
                }
                o[0] = __uint_as_float((uint32_t)v.x << 16); o[1] = rcp_apx(__uint_as_float((uint32_t)v.x & 0xffff0000u));
                o[2] = __uint_as_float((uint32_t)v.y << 16); o[3] = rcp_apx(__uint_as_float((uint32_t)v.y & 0xffff0000u));
                row = 2 * j;
            } else {
#pragma unroll
                for (int i = 0; i < 4; i++) {
                    const bool up = kg & 2;
                    const float ss = __shfl_xor_sync(~0u, up ? s[i] : s[i + 4], 16), qq = __shfl_xor_sync(~0u, up ? q[i] : q[i + 4], 16);
                    s[i] = (up ? s[i + 4] : s[i]) + ss; q[i] = (up ? q[i + 4] : q[i]) + qq; p0[i] = up ? p0[i + 4] : p0[i];
                }
#pragma unroll
                for (int i = 0; i < 2; i++) {
                    const bool up = kg & 1;
                    const float ss = __shfl_xor_sync(~0u, up ? s[i] : s[i + 2], 8), qq = __shfl_xor_sync(~0u, up ? q[i] : q[i + 2], 8);
                    s[i] = (up ? s[i + 2] : s[i]) + ss; q[i] = (up ? q[i + 2] : q[i]) + qq; p0[i] = up ? p0[i + 2] : p0[i];
                }
                uint4* gp = g_halo + 86016 + mb * 512 + j;
                const float d0 = s[0] * (1.0f / 80.0f), d1 = s[1] * (1.0f / 80.0f);
                asm volatile("st.relaxed.gpu.global.v4.f32 [%0], {%1,%2,%3,%4};" ::"l"(gp + hg * 64), "f"(p0[0] + d0), "f"(fmaxf(fmaf(-d0, s[0], q[0]), 0.f)), "f"(p0[1] + d1), "f"(fmaxf(fmaf(-d1, s[1], q[1]), 0.f)) : "memory");
                __nanosleep(ST_SLEEP0);
                uint32_t pw[8][4], todo = 0xff;
#pragma unroll 1
                for (int it = 0; it < SPIN_MAX; it++) {
#pragma unroll
                    for (int k = 0; k < 8; k++)
                        if (todo >> k & 1) asm volatile("ld.relaxed.gpu.global.v4.u32 {%0,%1,%2,%3}, [%4];" : "=r"(pw[k][0]), "=r"(pw[k][1]), "=r"(pw[k][2]), "=r"(pw[k][3]) : "l"(gp + k * 64) : "memory");
#pragma unroll
                    for (int k = 0; k < 8; k++)
                        if (__all_sync(~0u, pw[k][0] != ~0u && pw[k][1] != ~0u && pw[k][2] != ~0u && pw[k][3] != ~0u)) todo &= ~(1u << k);
                    if (!todo) break;
                    __nanosleep(ST_SLEEP);
                }
#pragma unroll
                for (int r = 0; r < 2; r++) {
                    float mean = 0.f, m2 = 0.f;
#pragma unroll
                    for (int k = 0; k < 8; k++) mean += __uint_as_float(pw[k][2 * r]);
                    mean *= 0.125f;
#pragma unroll
                    for (int k = 0; k < 8; k++) {
                        const float dm = __uint_as_float(pw[k][2 * r]) - mean;
                        m2 += fmaf(80.0f * dm, dm, __uint_as_float(pw[k][2 * r + 1]));
                    }
                    o[2 * r] = rbf(mean);
                    o[2 * r + 1] = rcp_apx(rbf(sqrt_apx(rbf(rbf(m2 * (1.0f / DM)) + 1e-5f))));
                }
                row = (j >> 5) * 64 + (j & 7) * 8 + ((j >> 3) & 3) * 2;
                if (hg == 0) *reinterpret_cast<uint32_t*>(g_piv + SEQ + mb * 128 + 2 * (row & 60) + 4 * (row >> 6) + (row & 3)) = __byte_perm(__float_as_uint(o[0]), __float_as_uint(o[2]), 0x7632);
            }
#pragma unroll
            for (int r = 0; r < 2; r++)
                *reinterpret_cast<uint4*>(stg + A1_SM_XA + (row + r) * 16) = make_uint4(__byte_perm(__float_as_uint(-o[2 * r]), 0, 0x3232), __float_as_uint(-o[2 * r]) >> 16, 0u, 0u);
            *reinterpret_cast<float4*>(rst + row + (row >> 6) * 8) = make_float4(o[0], o[1], o[2], o[3]);
            fence_async_smem();
            TSTAMP1T(7, 320); CSA(1);
            if (tid == 320) DBGC(44);
            __syncwarp();
            if ((tid & 31) == 0) mbar_arrive(bar_stat);
        }
        CSA(4); CSA_END;
        if (tid == 320) DBGCAL(0);
        __syncwarp();
        if (w == WOT) {
            mbar_wait(bars + 416, 0);
            mbar_wait(bar_done, 0);
            if (one) {
                bulk_load(sbase, wo + (hg * 8 + 6) * WOB, 2 * WOB, bar_wo);
                bulk_load(sbase + A1_SM_W0 + 2 * WOB, wo + (hg * 8 + 2) * WOB, WOB, bar_wo);
            }
            __syncwarp();
        }
#define FWA 11
#define FWB 10
        if (w == FWA || w == FWB) {
            const int cw = w == FWB;
            const uint32_t* fl = reinterpret_cast<const uint32_t*>(rsum + 2 * SEQ) + (((layer * 16 + mb) * 2 + cw) * 8 + (tid & 7)) * FSTR;
            const unsigned char* src = reinterpret_cast<const unsigned char*>(of) + mb * 163840 + cw * 10240 + (tid & 7) * 20480;
            const uint32_t sl = sbase + (cw ? A1_SM_A1 : A1_SM_A0);
            mbar_wait(cw ? bar_done : bar_kvf, 0);
            if (one) {
                mbar_expect_tx(bar_f2 + 64 * cw + 64, 10240);
                tma_load_3d(sl + 51200, &tmR, layer ? 0 : hg * 80, layer ? hg * 80 : mb * 64, layer ? mb * 2 + cw : cw, bar_f2 + 64 * cw + 64);
            }
            __syncwarp();
            uint32_t pend = 0xffu & ~(1u << hg), v = 0;
            const uint32_t bo = wo_off((tid & 7) + ((tid & 7) < hg)) >> 4, lt = (1u << (tid & 31)) - 1;
#pragma unroll 1
            for (int it = 0; pend && it < 2 * SPIN_MAX; it++) {
                if (v != 4 && (pend >> (tid & 31) & 1)) asm volatile(A1_FLD " %0, [%1];" : "=r"(v) : "l"(fl) : "memory");
                uint32_t fr;
                asm volatile("{\n.reg .pred p;\nmbarrier.test_wait.parity.shared::cta.b64 p, [%1], 0;\nselp.b32 %0, 1, 0, p;\n}" : "=r"(fr) : "r"(bar_e2 + 16 * cw + (tid & 1) * 8) : "memory");
                fr = __ballot_sync(~0u, fr);
                uint32_t m = __ballot_sync(~0u, v == 4 || it >= A1_FSPIN) & pend;
                const int q = 8 - __popc(pend) + __popc(m & lt);
                m &= __ballot_sync(~0u, q < ((fr & 2) ? 8 : (fr & 1) ? 7 : 5));
                pend ^= m;
                if (m >> (tid & 31) & 1) DBGC(12 + cw * 8 + (tid & 7));
                if (!m) __nanosleep(A1_FSLEEP);
                if (m >> (tid & 31) & 1) {
                    bulk_load(q == 7 && !cw ? sbase + A1_SM_W0 : sl + (q < 6 ? q : q - 6) * 10240, src, 10240, bar_f2 + 64 * cw + 8 * q);
                    asm volatile("st.shared.u32 [%0], %1;" ::"r"(que + 32 * cw + 4 * q), "r"(bo) : "memory");
                    mbar_expect_tx(bar_f2 + 64 * cw + 8 * q, 10240);
                    DBGC(44 + cw * 8 + q);
                }
                __syncwarp();
            }
        }
    } else if (tile < 128) {
        SPAN(1 + 4 * layer, 0);
        constexpr int on = 1;
        float acc[120];
        const int lane = tid & 31, warp = w & 7, g = lane >> 2, t = lane & 3;
        if (on) {
            SPAN(1 + 4 * layer, 1);
            TSTAMP1(0);
            if (threadIdx.x == 0) { GSTAMP(g_tim1, 15); }
            TSTAMP3(0);
            if (tid == 0) TSTAMP2(0);
            TSTAMP4(0);
            if (tid == 0) DBGC(60);
            if (layer == 0) a1_mainloop<0>(acc, sbase, bars, wg, tile); else a1_mainloop<1>(acc, sbase, bars, wg, tile);
            uint32_t ok;
            asm volatile("{\n.reg .pred p;\nmbarrier.test_wait.parity.shared::cta.b64 p, [%1], 0;\nselp.b32 %0, 1, 0, p;\n}" : "=r"(ok) : "r"(bar_stat) : "memory");
            if (tid == 128 && !ok) mbar_arrive(bars + 160);
            __syncwarp();
            mbar_wait(bar_stat, 0);
            wgmma_fence();
            wgmma_n240<0, 0>(acc, make_desc(sbase + A1_SM_XA + wg * 1024, 0, 128, 0), make_desc(sbase + A1_SM_XB, 0, 128, 0), 1);
            wgmma_commit();
            if (tid == 128 && ok) mbar_arrive(bars + 160);
            mbar_wait(bars + 8 * (A1_NST + 3), 1);
        }
        const float2* rw = rst + 16 * warp + 8 * wg;
        const float rb0 = rw[g + 8].y, ra = rw[g].y * 0.22360679774997896f, rb = rb0 * 0.22360679774997896f;
        wgmma_wait<0>();
        if ((tid & 127) == 0) mbar_arrive(bar_done);
        TSTAMP1(2); CSA(1);
        TSTAMP1T(13, 224);
        if ((tid & 127) == 0) DBGC(62 - wg);
        uint32_t f[2][30];
#pragma unroll
        for (int j = 10; j < 30; j++) f[1][j] = pack2(acc[4 * j + 2], acc[4 * j + 3]);
        if ((warp & 3) == 3) {
            uint4* hout = g_halo + (((layer * 16 + mb) * 8 + hg) * 2 + wg) * 168;
#pragma unroll
            for (int j = 0; j < 20; j += 4) {
                const int a = j < 12 ? 10 + j : 8 + j, b = j == 8 ? 28 : a + 2;
                asm volatile("st.relaxed.gpu.global.v4.u32 [%0], {%1,%2,%3,%4};" ::"l"(hout + 8 * j + lane), "r"(f[1][a]), "r"(f[1][a + 1]), "r"(f[1][b]), "r"(f[1][b + 1]) : "memory");
            }
            if (t == 0) asm volatile("st.relaxed.gpu.global.f32 [%0], %1;" ::"l"(reinterpret_cast<float*>(hout + 160) + g), "f"(rb0) : "memory");
        }
        TSTAMP1T(12, 224);
        const uint32_t kvw = sbase + A1_SM_KV + (16 * warp + 8 * wg) * A1_KVP;
        const uint32_t mrow = kvw + (lane & 7) * A1_KVP + (lane >> 3) * 16;
#pragma unroll
        for (int j = 0; j < 20; j += 4) stsm_x4(mrow + 16 * A1_KVP + 16 * j, f[1][10 + j], f[1][11 + j], f[1][12 + j], f[1][13 + j]);
        __syncwarp();
        if (lane == 0 && (warp & 3) != 3) mbar_arrive(bar_kv + 8 * (warp + 1));
#pragma unroll
        for (int j = 0; j < 30; j++) f[0][j] = pack2(acc[4 * j], acc[4 * j + 1]);
        stsm_x4(mrow + 8 * A1_KVP + 160, f[0][20], f[0][21], f[0][22], f[0][23]);
        stsm_x4(mrow + 8 * A1_KVP + 224, f[0][24], f[0][25], f[0][26], f[0][27]);
        asm volatile("stmatrix.sync.aligned.m8n8.x2.shared.b16 [%0], {%1,%2};" ::"r"(mrow + 8 * A1_KVP + 288), "r"(f[0][28]), "r"(f[0][29]) : "memory");
#pragma unroll
        for (int j = 0; j < 10; j++) f[1][j] = pack2(acc[4 * j + 2], acc[4 * j + 3]);
        __syncwarp();
        uint32_t vb[10][2], hv[24] = {}, *kp = hv, *vp = hv + 12;
#pragma unroll
        for (int j = 0; j < 10; j += 2) ldsm_x4_t(&vb[j][0], kvw + (8 + (lane & 15)) * A1_KVP + 160 + (lane >> 4) * 16 + 16 * j);
        const bool up0 = 2 * t > g, up1 = 2 * t + 1 > g, edge = (mb | (warp & 3)) == 0;
        float rk[4];
        auto above = [&]() {
            mbar_wait(bar_kv + 8 * warp, 0);
#pragma unroll
            for (int j = 0; j < 12; j += 4) ldsm_x4(&kp[j], mrow + 16 * j);
            rk[0] = rw[2 * t - (up0 ? 8 : 0)].y; rk[1] = rw[2 * t + 1 - (up1 ? 8 : 0)].y;
#pragma unroll
            for (int j = 0; j < 12; j += 4) ldsm_x4_t(&vp[j], mrow + 160 + 16 * j - (j == 8 ? (lane & 16) * 2 : 0));
            __syncwarp();
            if (lane == 0) mbar_arrive(bar_kvf);
        };
        const uint4* hin = g_halo + (((layer * 16 + mb - 1) * 8 + hg) * 2 + wg) * 168;
        auto ask = [&]() {
            if (mb > 0) {
#pragma unroll
                for (int k = 0; k < 20; k += 4)
                    asm volatile("ld.relaxed.gpu.global.v4.u32 {%0,%1,%2,%3}, [%4];" : "=r"(hv[k]), "=r"(hv[k + 1]), "=r"(hv[k + 2]), "=r"(hv[k + 3]) : "l"(hin + 8 * k + lane) : "memory");
                asm volatile("ld.relaxed.gpu.global.v2.u32 {%0,%1}, [%2];" : "=r"(hv[20]), "=r"(hv[21]) : "l"(reinterpret_cast<const uint2*>(hin + 160) + t) : "memory");
            }
        };
        auto halo = [&]() {
            if (lane == 0) mbar_arrive(bar_kvf);
            rk[0] = rw[2 * t].y; rk[1] = rw[2 * t + 1].y;
#pragma unroll 1
            for (int it = 0; it < SPIN_MAX; it++) {
                uint32_t m = max(hv[20], hv[21]);
#pragma unroll
                for (int k = 0; k < 20; k += 2) m = __vimax3_u32(m, hv[k], hv[k + 1]);
                if (!__any_sync(~0u, m == ~0u)) break;
                ask();
            }
            if (wg && lane == 0) mbar_arrive(bars + 416);
            if (up0) rk[0] = __uint_as_float(hv[20]);
            if (up1) rk[1] = __uint_as_float(hv[21]);
#pragma unroll
            for (int j = 0; j < 10; j++) asm volatile("movmatrix.sync.aligned.m8n8.trans.b16 %0, %1;" : "=r"(vp[j]) : "r"(hv[j < 8 ? 12 + j : 2 + j]));
        };
        rk[2] = rw[2 * t + (up0 ? 0 : 8)].y; rk[3] = rw[2 * t + 1 + (up1 ? 0 : 8)].y;
        uint32_t qs[4][2];
#pragma unroll
        for (int h = 0; h < 4; h++) {
            qs[h][0] = (t >> 1) == (h & 1) ? f[0][5 * (h >> 1) + 2] : 0u; qs[h][1] = (t >> 1) == (h & 1) ? f[1][5 * (h >> 1) + 2] : 0u;
            asm volatile("" : "+r"(qs[h][0]), "+r"(qs[h][1]));
        }
#pragma unroll
        for (int j = 0; j < 10; j++) asm volatile("" : "+r"(f[0][j]), "+r"(f[1][j]), "+r"(f[0][10 + j]));
        if (warp & 3) above(); else if (wg) ask();
        TSTAMP1T(10, 64); CSA(2);
        if (warp && !wg) mbar_wait(bars + 416 + 8 * warp, 0);
        CSA(3);
        float sc[4][3][4];
#pragma unroll
        for (int h = 0; h < 4; h++) {
            const int jb = 5 * (h >> 1) + 3 * (h & 1), js = 5 * (h >> 1) + 2;
#pragma unroll
            for (int nt = 1; nt < 3; nt++) {
#pragma unroll
                for (int e = 0; e < 4; e++) sc[h][nt][e] = 0.f;
                mma_bf16(sc[h][nt], f[0][jb], f[1][jb], f[0][jb + 1], f[1][jb + 1], f[nt - 1][10 + jb], f[nt - 1][11 + jb]);
                mma_bf16_k8(sc[h][nt], qs[h][0], qs[h][1], f[nt - 1][10 + js]);
            }
        }
        if (warp == 0) ask();
        if (!(warp & 3)) halo();
        TSTAMP1(8); CSA(4);
#pragma unroll
        for (int h = 0; h < 4; h++) {
            const int jb = 5 * (h >> 1) + 3 * (h & 1), js = 5 * (h >> 1) + 2;
#pragma unroll
            for (int e = 0; e < 4; e++) sc[h][0][e] = 0.f;
            mma_bf16(sc[h][0], f[0][jb], f[1][jb], f[0][jb + 1], f[1][jb + 1], kp[jb], kp[jb + 1]);
            mma_bf16_k8(sc[h][0], qs[h][0], qs[h][1], kp[js]);
        }
        TSTAMP1T(3, 64);
        float p[4][4], sum[4][2];
        uint32_t lg[4][2], mx[4];
        const float rl[4] = {rk[0] * ra, rk[1] * ra, rk[2] * rb, rk[3] * rb};
        auto max2 = [](uint32_t a, uint32_t b) { uint32_t r; asm("max.bf16x2 %0, %1, %2;" : "=r"(r) : "r"(a), "r"(b)); return r; };
#pragma unroll
        for (int h = 0; h < 4; h++) {
            lg[h][0] = pack2((up0 ? sc[h][0][0] : sc[h][1][0]) * rl[0], (up0 ? sc[h][1][2] : sc[h][2][2]) * rl[2]);
            lg[h][1] = pack2((up1 ? sc[h][0][1] : sc[h][1][1]) * rl[1], (up1 ? sc[h][1][3] : sc[h][2][3]) * rl[3]);
            if (edge) {
                if (up0) lg[h][0] = __byte_perm(lg[h][0], 0xce6eu, 0x3254);
                if (up1) lg[h][1] = __byte_perm(lg[h][1], 0xce6eu, 0x3254);
            }
            mx[h] = max2(lg[h][0], lg[h][1]);
        }
#pragma unroll
        for (int o = 1; o <= 2; o <<= 1)
#pragma unroll
            for (int h = 0; h < 4; h++) mx[h] = max2(mx[h], __shfl_xor_sync(~0u, mx[h], o));
#pragma unroll
        for (int h = 0; h < 4; h++)
#pragma unroll
            for (int r = 0; r < 2; r++) {
                const float m = __uint_as_float(r ? mx[h] & 0xffff0000u : mx[h] << 16);
#pragma unroll
                for (int e = 0; e < 2; e++)
                    asm("ex2.approx.ftz.f32 %0, %1;" : "=f"(p[h][2 * r + e]) : "f"((__uint_as_float(r ? lg[h][e] & 0xffff0000u : lg[h][e] << 16) - m) * 1.4426950408889634f));
                sum[h][r] = p[h][2 * r] + p[h][2 * r + 1];
            }
#pragma unroll
        for (int o = 1; o <= 2; o <<= 1)
#pragma unroll
            for (int h = 0; h < 4; h++)
#pragma unroll
                for (int r = 0; r < 2; r++) sum[h][r] += __shfl_xor_sync(~0u, sum[h][r], o);
        TSTAMP1T(5, 64); CSA(5);
        const uint32_t mu = (up0 ? 0xffffu : 0u) | (up1 ? 0xffff0000u : 0u);
        uint32_t ob[10][2];
#pragma unroll
        for (int P = 0; P < 2; P++) {
            float os[2][4];
#pragma unroll
            for (int e = 0; e < 2; e++) {
                const int h = 2 * P + e;
                const float i0 = rcp_apx(sum[h][0]), i1 = rcp_apx(sum[h][1]);
                const uint32_t w0 = pack2(p[h][0] * rk[0] * i0, p[h][1] * rk[1] * i0), w1 = pack2(p[h][2] * rk[2] * i1, p[h][3] * rk[3] * i1);
#pragma unroll
                for (int dt = 0; dt < 3; dt++) {
                    const int j = 5 * P + (dt < 2 ? 3 * e + dt : 2);
                    float o[4] = {0.f, 0.f, 0.f, 0.f};
                    mma_bf16(o, w0 & ~mu, w1 & mu, 0u, w1 & ~mu, vb[j][0], vb[j][1]);
                    mma_bf16_k8(o, w0 & mu, 0u, vp[j]);
                    if (dt < 2) { ob[j][0] = pack2(o[0], o[1]); ob[j][1] = pack2(o[2], o[3]); }
                    else { os[e][0] = o[0]; os[e][1] = o[1]; os[e][2] = o[2]; os[e][3] = o[3]; }
                }
            }
#pragma unroll
            for (int k = 0; k < 4; k++) os[0][k] = t < 2 ? os[0][k] : os[1][k];
            ob[5 * P + 2][0] = pack2(os[0][0], os[0][1]); ob[5 * P + 2][1] = pack2(os[0][2], os[0][3]);
        }
        const uint32_t sl = sbase + (wg ? A1_SM_A1 : A1_SM_A0);
        const uint32_t o0 = (warp & 3) * 2048 + g * 64 + ((t ^ (g >> 1)) << 4), o1 = 8192 + (warp & 3) * 512 + g * 32 + ((t ^ ((g >> 2) << 1)) << 3);
        CSA(15);
#pragma unroll
        for (int j = 0; j < 10; j++) asm volatile("" : "+r"(ob[j][0]), "+r"(ob[j][1]) :: "memory");
        if (wg == 0 && lane == 0) mbar_arrive(bar_pv);
        mbar_wait(bar_done, 0);
        if (wg == 0) mbar_wait(bar_kvf, 0);
#pragma unroll
        for (int h = 0; h < 2; h++) {
            asm volatile("st.shared.v4.u32 [%0], {%1,%2,%3,%4};" ::"r"(sl + o0 + h * 1024), "r"(ob[0][h]), "r"(ob[1][h]), "r"(ob[2][h]), "r"(ob[3][h]) : "memory");
            asm volatile("st.shared.v4.u32 [%0], {%1,%2,%3,%4};" ::"r"(sl + o0 + h * 1024 + 512), "r"(ob[4][h]), "r"(ob[5][h]), "r"(ob[6][h]), "r"(ob[7][h]) : "memory");
            asm volatile("st.shared.v2.u32 [%0], {%1,%2};" ::"r"(sl + o1 + h * 256), "r"(ob[8][h]), "r"(ob[9][h]) : "memory");
        }
        if (warp > 4 && lane == 0) mbar_arrive(bars + 384 + 8 * warp);
        fence_async_smem();
        __syncwarp();
        TSTAMP1T(4, 64); CSA(6);
        TSTAMP1(1);
        TSTAMP2(1);
        const unsigned char* ot = reinterpret_cast<const unsigned char*>(of) + mb * 163840 + wg * 10240;
        if (lane == 0) {
            asm volatile("cp.async.bulk.global.shared::cta.bulk_group [%0], [%1], 2048;" ::"l"(ot + hg * 20480 + (warp & 3) * 2048), "r"(sl + (warp & 3) * 2048) : "memory");
            asm volatile("cp.async.bulk.global.shared::cta.bulk_group [%0], [%1], 512;" ::"l"(ot + hg * 20480 + 8192 + (warp & 3) * 512), "r"(sl + 8192 + (warp & 3) * 512) : "memory");
            asm volatile("cp.async.bulk.commit_group;" ::: "memory");
            asm volatile("cp.async.bulk.wait_group 0;" ::: "memory");
            asm volatile(A1_FRED " [%0], 1;" ::"l"(reinterpret_cast<uint32_t*>(rsum + 2 * SEQ) + (((layer * 16 + mb) * 2 + wg) * 8 + hg) * FSTR) : "memory");
            DBGC(4 + warp);
        }
        TSTAMP4(11); CSA(7);
        float ac2[40];
        const uint64_t db0 = make_desc(sbase, 1024, 256, 3), db1 = make_desc(sbase + 10240, 512, 256, 3), da0 = make_desc(sl, 16, 1024, 2), da1 = make_desc(sl + 8192, 16, 256, 3);
        const uint32_t o7 = wg ? 640 : (A1_SM_W0 - A1_SM_A0) >> 4;
        const uint32_t trow = ((lane & 7) + 8 * (lane >> 4)) * 128 + (((2 * (warp & 3) + ((lane >> 3) & 1)) ^ (lane & 7)) << 4);
        uint32_t xr[10][2];
        mbar_wait(bar_f2 + 64 * wg + 64, 0);
        if (layer == 0) {
#pragma unroll
            for (int j = 0; j < 10; j += 2) ldsm_x4(&xr[j][0], sl + 51200 + (16 * (warp & 3) + (lane & 15)) * 160 + (lane >> 4) * 16 + 16 * j);
        } else {
#pragma unroll
            for (int j = 0; j < 10; j += 2) ldsm_x4_t(&xr[j][0], sl + 51200 + trow + 1024 * j);
        }
        const uint32_t ri = __shfl_sync(~0u, layer * SEQ + (wg * 2 + ((g >> 1) & 1)) * 512 + (mb * 16 + 4 * (warp & 3) + (g >> 2)) * 2 + (g & 1), lane);
        mbar_wait(bar_wo, 0);
        if (wg) asm volatile("bar.sync 2, 128;" ::: "memory"); else asm volatile("bar.sync 1, 128;" ::: "memory");
        if (wg) mbar_wait(bar_pv, 0);
        TSTAMP2(2); CSA(8);
#pragma unroll
        for (int q = 0; q < 8; q++) {
            uint32_t bo = wo_off(0) >> 4;
            if (q) {
                mbar_wait(bar_f2 + 64 * wg + 8 * q, 0);
                asm volatile("ld.shared.u32 %0, [%1];" : "=r"(bo) : "r"(que + 32 * wg + 4 * q) : "memory");
                bo = __shfl_sync(~0u, bo, 0);
                TSTAMP4(q);
                if (q % 3 == 1) CSA(9 + q / 3);
                if (q == 1 && (tid & 127) == 0) DBGC(29 + 8 * wg);
            }
            wgmma_fence();
#pragma unroll
            for (int j = 0; j < 5; j++) wgmma_n80(ac2, (j < 4 ? da0 : da1) + (q == 7 ? o7 : 0u) + (uint64_t)((q < 6 ? q * 640 : 0) + (j & 2) * 16 + (j & 1) * 2), (j < 4 ? db0 : db1) + bo + (uint64_t)((j & 2) * 160 + (j & 1) * 32), j || q);
            wgmma_commit();
            if (q == 0) {
                wgmma_wait<0>();
                if ((tid & 127) == 0) { mbar_arrive(bar_e2 + 16 * wg); mbar_arrive(bar_e2 + 8); }
            }
            if (q == 2 && wg) {
                wgmma_wait<1>();
                if (tid == 128) mbar_arrive(bar_e2 + 24);
            }
        }
        if ((tid & 127) == 0) DBGC(28 + wg * 8 + 7);
        TSTAMP2(3);
        wgmma_wait<0>();
        TSTAMP2(4); CSA(12);
        if (__any_sync(~0u, ac2[0] != ac2[0] || ac2[2] != ac2[2])) {
#pragma unroll
            for (int i = 0; i < 40; i++) ac2[i] = 0.f;
            uint32_t a[20], an[20];
            auto lda = [&](uint32_t (&r)[20], int h) {
#pragma unroll
                for (int u = 0; u < 4; u++)
                    asm volatile("ld.relaxed.gpu.global.v4.u32 {%0,%1,%2,%3}, [%4];" : "=r"(r[4 * u]), "=r"(r[4 * u + 1]), "=r"(r[4 * u + 2]), "=r"(r[4 * u + 3]) : "l"(ot + h * 20480 + o0 + u * 512) : "memory");
#pragma unroll
                for (int u = 0; u < 2; u++)
                    asm volatile("ld.relaxed.gpu.global.v2.u32 {%0,%1}, [%2];" : "=r"(r[16 + 2 * u]), "=r"(r[17 + 2 * u]) : "l"(ot + h * 20480 + o1 + u * 256) : "memory");
            };
            lda(an, 0);
#pragma unroll 5
            for (int k = lane; k < WOB / 16; k += 32)
                reinterpret_cast<uint4*>(stg + (sl - sbase))[k] = __ldcg(reinterpret_cast<const uint4*>(wo + hg * 8 * WOB) + k);
            __syncwarp();
#pragma unroll 1
            for (int h = 0; h < 8; h++) {
#pragma unroll 1
                for (int it = 0; it < SPIN_MAX; it++) {
                    uint32_t m = 0;
#pragma unroll
                    for (int k = 0; k < 20; k += 2) m = __vimax3_u32(m, an[k], an[k + 1]);
                    if (!__any_sync(~0u, m == ~0u)) break;
                    lda(an, h);
                }
#pragma unroll
                for (int k = 0; k < 20; k++) a[k] = an[k];
                lda(an, min(h + 1, 7));
                const uint32_t bp = h == hg ? sl : sbase + wo_off(h + (h < hg));
                const int r0 = 8 * ((lane & 7) >> 1) + 2 * (lane >> 3) + (lane & 1), r2 = 4 * ((lane & 7) >> 1) + 2 * ((lane >> 3) & 1) + (lane & 1);
#pragma unroll
                for (int n = 0; n < 10; n++) {
                    uint32_t b[12];
                    ldsm_x4_t(b, bp + (n >> 1) * 1024 + r0 * 32 + (((n ^ (r0 >> 2)) & 1) << 4));
                    ldsm_x4_t(b + 4, bp + 5120 + (n >> 1) * 1024 + r0 * 32 + (((n ^ (r0 >> 2)) & 1) << 4));
                    ldsm_x4_t(b + 8, bp + 10240 + (n >> 1) * 512 + r2 * 32 + (((n ^ (r2 >> 2)) & 1) << 4));
                    mma_bf16(ac2 + 4 * n, a[0], a[8], a[1], a[9], b[0], b[1]); mma_bf16(ac2 + 4 * n, a[2], a[10], a[3], a[11], b[2], b[3]);
                    mma_bf16(ac2 + 4 * n, a[4], a[12], a[5], a[13], b[4], b[5]); mma_bf16(ac2 + 4 * n, a[6], a[14], a[7], a[15], b[6], b[7]);
                    mma_bf16(ac2 + 4 * n, a[16], a[18], a[17], a[19], b[8], b[9]);
                }
            }
        }
#pragma unroll
        for (int j = 0; j < 10; j++)
#pragma unroll
            for (int hh = 0; hh < 2; hh++) {
                const uint32_t a = pack2(ac2[4 * j + 2 * hh], ac2[4 * j + 2 * hh + 1]);
                const __nv_bfloat162 r = __hadd2_rn(*reinterpret_cast<const __nv_bfloat162*>(&xr[j][hh]), *reinterpret_cast<const __nv_bfloat162*>(&a));
                xr[j][hh] = *reinterpret_cast<const uint32_t*>(&r);
            }
        const uint32_t so = sl + 30720;
#pragma unroll
        for (int j = 0; j < 10; j += 2) stsm_x4_t(so + trow + 1024 * j, xr[j][0], xr[j][1], xr[j + 1][0], xr[j + 1][1]);
        if (wg) asm volatile("bar.sync 2, 128;" ::: "memory"); else asm volatile("bar.sync 1, 128;" ::: "memory");
        TSTAMP2(5); CSA(13);
        if ((tid & 127) == 0) {
            fence_async_smem();
            asm volatile("cp.async.bulk.tensor.2d.global.shared::cta.bulk_group [%0, {%1, %2}], [%3];" ::"l"(&tmX1), "r"(mb * 128 + 64 * wg), "r"(hg * 80), "r"(so) : "memory");
            asm volatile("cp.async.bulk.commit_group;" ::: "memory");
        }
        __syncwarp();
        const float p0 = *(volatile const float*)&rw[g].x, p1 = *(volatile const float*)&rw[g + 8].x;
        float s[3][4] = {};
        const uint32_t pp[2] = {__byte_perm(__float_as_uint(p0), 0, 0x3232), __byte_perm(__float_as_uint(p1), 0, 0x3232)};
#pragma unroll
        for (int j = 0; j < 10; j += 2) {
            const uint32_t d0 = sub2(xr[j][0], pp[0]), d1 = sub2(xr[j][1], pp[1]), d2 = sub2(xr[j + 1][0], pp[0]), d3 = sub2(xr[j + 1][1], pp[1]);
            mma_bf16(s[0], xr[j][0], xr[j][1], xr[j + 1][0], xr[j + 1][1], 0x3f803f80u, 0x3f803f80u);
            mma_bf16(s[1], d0, d1, d2, d3, d0, d2);
            mma_bf16(s[2], d0, d1, d2, d3, d1, d3);
        }
        if (t == (g >> 1)) {
            float2* rp = rsum + ri;
            asm volatile("red.relaxed.gpu.global.add.v2.f32 [%0], {%1, %2};" ::"l"(rp), "f"(fmaf(-80.f, p0, s[0][0])), "f"((g & 1) ? s[1][1] : s[1][0]) : "memory");
            asm volatile("red.relaxed.gpu.global.add.v2.f32 [%0], {%1, %2};" ::"l"(rp + 4), "f"(fmaf(-80.f, p1, s[0][2])), "f"((g & 1) ? s[2][3] : s[2][2]) : "memory");
        }
        asm volatile("cp.async.bulk.wait_group.read 0;" ::: "memory");
        TSTAMP2(6); CSA(14); CSA_END;
        if (tid == 0) DBGC(63);
        if (tid == 128) DBGC(28);
        if (tid == 0) DBGCAL(2);
        GSTAMP(g_tim1, 14);
        SPAN(1 + 4 * layer, 3);
    }
#undef layer
}

static int h_nsm;
static void* h_sym[11];
static TileTab h_tab[2];
static CUtensorMap h_tmX0, h_tmX1, h_tmR0, h_tmR1, h_tmX1st, h_tmOut;
static KgMaps h_tmW;
typedef CUresult (*PFN_encodeTiled)(CUtensorMap*, CUtensorMapDataType, cuuint32_t, void*, const cuuint64_t*, const cuuint64_t*,
                                    const cuuint32_t*, const cuuint32_t*, CUtensorMapInterleave, CUtensorMapSwizzle,
                                    CUtensorMapL2promotion, CUtensorMapFloatOOBfill);
static void make_tmap(CUtensorMap* tm, const void* ptr, uint64_t cols, uint64_t rows, uint32_t bc, uint32_t br, CUtensorMapSwizzle sw, uint64_t pitch = 0, uint64_t hi = 0, uint32_t bh = 2) {
    static PFN_encodeTiled fn = nullptr;
    if (!fn) {
        void* p = nullptr; cudaDriverEntryPointQueryResult qr;
        cudaGetDriverEntryPoint("cuTensorMapEncodeTiled", &p, cudaEnableDefault, &qr);
        fn = (PFN_encodeTiled)p;
    }
    if (br == 0) {
        cuuint64_t dims[5] = {16, 2, rows / 8, 4, cols / 16}; cuuint64_t strides[4] = {cols * 2, cols * 16, cols * 4, 32};
        cuuint32_t box[5] = {16, 2, bc, 4, 5}; cuuint32_t es[5] = {1, 1, 1, 1, 1};
        fn(tm, CU_TENSOR_MAP_DATA_TYPE_BFLOAT16, 5, const_cast<void*>(ptr), dims, strides, box, es, CU_TENSOR_MAP_INTERLEAVE_NONE, sw,
           CU_TENSOR_MAP_L2_PROMOTION_L2_128B, CU_TENSOR_MAP_FLOAT_OOB_FILL_NONE);
        return;
    }
    if (hi == 16) {
        cuuint64_t dims[4] = {16, 32, 120, 20}; cuuint64_t strides[3] = {3840, 32, 32 * 3840};
        cuuint32_t box[4] = {16, 32, 5, 2}; cuuint32_t es[4] = {1, 1, 1, 1};
        fn(tm, CU_TENSOR_MAP_DATA_TYPE_BFLOAT16, 4, const_cast<void*>(ptr), dims, strides, box, es, CU_TENSOR_MAP_INTERLEAVE_NONE, sw,
           CU_TENSOR_MAP_L2_PROMOTION_L2_128B, CU_TENSOR_MAP_FLOAT_OOB_FILL_NONE);
        return;
    }
    if (bh == 0) {
        cuuint64_t dims[5] = {64, 64, 2, 16, 10}; cuuint64_t strides[4] = {pitch * 2, hi * 2, cols * 2, rows * 2};
        cuuint32_t box[5] = {64, 64, 2, 1, 1}; cuuint32_t es[5] = {1, 1, 1, 1, 1};
        fn(tm, CU_TENSOR_MAP_DATA_TYPE_BFLOAT16, 5, const_cast<void*>(ptr), dims, strides, box, es, CU_TENSOR_MAP_INTERLEAVE_NONE, sw,
           CU_TENSOR_MAP_L2_PROMOTION_L2_128B, CU_TENSOR_MAP_FLOAT_OOB_FILL_NONE);
        return;
    }
    if (hi) {
        cuuint64_t dims[3] = {cols, rows, hi == 64 ? 32u : 2u}; cuuint64_t strides[2] = {pitch * 2, hi * 2};
        cuuint32_t box[3] = {bc, br, bh}; cuuint32_t es[3] = {1, 1, 1};
        fn(tm, CU_TENSOR_MAP_DATA_TYPE_BFLOAT16, 3, const_cast<void*>(ptr), dims, strides, box, es, CU_TENSOR_MAP_INTERLEAVE_NONE, sw,
           CU_TENSOR_MAP_L2_PROMOTION_L2_128B, CU_TENSOR_MAP_FLOAT_OOB_FILL_NONE);
        return;
    }
    cuuint64_t dims[2] = {cols, rows}; cuuint64_t strides[1] = {(pitch ? pitch : cols) * 2};
    cuuint32_t box[2] = {bc, br}; cuuint32_t es[2] = {1, 1};
    fn(tm, CU_TENSOR_MAP_DATA_TYPE_BFLOAT16, 2, const_cast<void*>(ptr), dims, strides, box, es, CU_TENSOR_MAP_INTERLEAVE_NONE, sw,
       CU_TENSOR_MAP_L2_PROMOTION_L2_128B, CU_TENSOR_MAP_FLOAT_OOB_FILL_NONE);
}
template <typename... Args>
static void launch_pdl(void (*kern)(Args...), int grid, int block, int smem, Args... args) {
    cudaLaunchConfig_t cfg = {};
    cfg.gridDim = dim3(grid); cfg.blockDim = dim3(block); cfg.dynamicSmemBytes = smem; cfg.stream = cudaStreamPerThread;
    cudaLaunchAttribute at[1];
    at[0].id = cudaLaunchAttributeProgrammaticStreamSerialization; at[0].val.programmaticStreamSerializationAllowed = 1;
    cfg.attrs = at; cfg.numAttrs = 1;
    cudaLaunchKernelEx(&cfg, kern, args...);
}
static void launch_stage(int k, void* const* d_in, void* d_out) {
    const Par par = {k > 1 ? nullptr : (const bf16*)d_in[4], (const bf16*)d_in[5], (const bf16*)d_in[6], (const bf16*)d_in[7], (const bf16*)d_in[8], (const bf16*)d_in[9], k > 1, 0, (const bf16*)d_in[0],
                     (uint4*)h_sym[4], (uint4*)h_sym[2], (uint4*)h_sym[6], (uint4*)h_sym[3], (uint4*)h_sym[0], (float*)h_sym[5], (uint4*)h_sym[1], (const bf16*)d_in[1], (const bf16*)d_in[2]};
    auto a1 = h_nsm == 132 ? a1_kernel<true> : a1_kernel<false>;
    switch (k) {
        case 1: a1<<<h_nsm, A1_THREADS, A1_SMEM, cudaStreamPerThread>>>(par, h_tmX0, h_tmR0, h_tmX1st, h_tmW, h_tab[0]); break;
        case 3: launch_pdl(conv_kernel, DM / CV_CPB, CV_THREADS, CV_SMEM, 0, (const uint4*)h_sym[7], (const float4*)h_sym[4], (const bf16*)h_sym[8], (bf16*)h_sym[9], (const uint4*)h_sym[0], h_tmOut); break;
        case 5: launch_pdl(a1, h_nsm, A1_THREADS, A1_SMEM, par, h_tmX1, h_tmR1, h_tmX1st, h_tmW, h_tab[1]); break;
        case 7: launch_pdl(conv_kernel, DM / CV_CPB, CV_THREADS, CV_SMEM, 1, (const uint4*)h_sym[7] + SEQ / 8, (const float4*)h_sym[4] + SEQ / 2, (const bf16*)h_sym[8], (bf16*)h_sym[10], (const uint4*)h_sym[0], h_tmOut); break;
        default: break;
    }
}
static int n_stage_kernels() { return 9; }
static const char* stage_name(int k) { const char* n[] = {"kgen", "a1", "a2", "conv", "tr", "a1", "a2", "conv", "tr"}; return n[k]; }

extern "C" void kernel_launch(void* const* d_in, const int* in_sizes, int n_in, void* d_out, int out_size) {
    (void)in_sizes; (void)n_in; (void)out_size;
    static const void *p_in = nullptr, *p_w1 = nullptr, *p_w2 = nullptr, *p_out = nullptr;
    if (p_in != d_in[0] || p_w1 != d_in[1] || p_w2 != d_in[2] || p_out != d_out) {
        cudaFuncSetAttribute(conv_kernel, cudaFuncAttributeMaxDynamicSharedMemorySize, CV_SMEM);
        cudaFuncSetAttribute(a1_kernel<true>, cudaFuncAttributeMaxDynamicSharedMemorySize, A1_SMEM);
        cudaFuncSetAttribute(a1_kernel<false>, cudaFuncAttributeMaxDynamicSharedMemorySize, A1_SMEM);
        int dev; cudaGetDevice(&dev); cudaDeviceGetAttribute(&h_nsm, cudaDevAttrMultiProcessorCount, dev);
        if (h_nsm != 132) h_nsm = 128;
        cudaGetSymbolAddress(&h_sym[0], g_tap); cudaGetSymbolAddress(&h_sym[1], g_wq); cudaGetSymbolAddress(&h_sym[2], g_wo);
        cudaGetSymbolAddress(&h_sym[3], g_halo); cudaGetSymbolAddress(&h_sym[4], g_sum); cudaGetSymbolAddress(&h_sym[5], g_csp); cudaGetSymbolAddress(&h_sym[6], g_of);
        cudaGetSymbolAddress(&h_sym[7], g_piv); cudaGetSymbolAddress(&h_sym[8], g_x1T); cudaGetSymbolAddress(&h_sym[9], g_xcT); cudaGetSymbolAddress(&h_sym[10], g_yT);
        for (int i = 0; i < 264; i++) {
            const int s = i % 132, h = (s - 64) >> 1;
            const int t = h_nsm != 132 ? s : s < 64 ? ((s >> 1) & 7) * 16 + (s >> 4) * 2 + (s & 1) : s < 120 ? (1 + h % 7) * 16 + 8 + (h / 7) * 2 + (s & 1) : s < 124 ? 128 : s - 116;
            const int hg = (4 * (t >> 6) + (t & 3)) & 7;
            const uint64_t wp = (uint64_t)h_sym[1] + hg * 10 * WQ_STAGE;
            h_tab[i / 132].e[s] = make_uint4((uint32_t)wp, (uint32_t)(wp >> 32), ((t >> 2) & 15) | (i / 132) << 4 | hg << 8 | 5 * (hg >> 2) << 16 | (uint32_t)t << 24, 0);
        }
        void *px1, *px2;
        cudaGetSymbolAddress(&px1, g_x1T); cudaGetSymbolAddress(&px2, g_xcT);
        make_tmap(&h_tmX0, d_in[0], 128 * 640, 64, 64, 64, CU_TENSOR_MAP_SWIZZLE_128B, 1280, 640, 0);
        make_tmap(&h_tmX1, px2, 128, 64 * XCP, 64, 64, CU_TENSOR_MAP_SWIZZLE_128B, XCP, 64, 0);
        make_tmap(&h_tmR0, d_in[0], 640, 1024, 80, 64, CU_TENSOR_MAP_SWIZZLE_NONE, 1280, 640, 1);
        make_tmap(&h_tmR1, px2, 64, 640, 64, 80, CU_TENSOR_MAP_SWIZZLE_128B, XCP, 64, 1);
        make_tmap(&h_tmX1st, px1, 2048, 640, 64, 80, CU_TENSOR_MAP_SWIZZLE_128B, XCP);
        make_tmap(&h_tmW.q, d_in[1], 16, 640, 16, 32, CU_TENSOR_MAP_SWIZZLE_32B, 1920, 16, 5);
        make_tmap(&h_tmW.o, d_in[2], 640, 640, 4, 0, CU_TENSOR_MAP_SWIZZLE_32B);
        make_tmap(&h_tmW.t, d_in[2], 640, 640, 2, 0, CU_TENSOR_MAP_SWIZZLE_32B);
        make_tmap(&h_tmOut, d_out, 640, 1024, 80, 8, CU_TENSOR_MAP_SWIZZLE_NONE, 1280, 640, 1);
        p_in = d_in[0]; p_w1 = d_in[1]; p_w2 = d_in[2]; p_out = d_out;
    }
    for (int k = 0; k < n_stage_kernels(); k++) launch_stage(k, d_in, d_out);
}
```

```cpp
#include <cuda_runtime.h>
#include <cuda_bf16.h>
#include <cuda_fp16.h>
#include <stdint.h>
#include <cuda.h>

typedef __nv_bfloat16 bf16;

constexpr int SEQ = 2048;
constexpr int DM = 640;
constexpr int NMODE = 192;

__device__ __forceinline__ float bf2f(bf16 v) { return __bfloat162float(v); }
__device__ __forceinline__ float rbf(float v) {
    uint32_t r;
    asm("cvt.rn.bf16x2.f32 %0, %1, %2;" : "=r"(r) : "f"(v), "f"(0.f));
    return __uint_as_float(r);
}
__device__ __forceinline__ uint32_t pack2(float lo, float hi) {
    __nv_bfloat162 t = __floats2bfloat162_rn(lo, hi);
    return *reinterpret_cast<uint32_t*>(&t);
}
__device__ __forceinline__ void pdl_sync() {
    asm volatile("griddepcontrol.wait;" ::: "memory");
    asm volatile("griddepcontrol.launch_dependents;" ::: "memory");
}
__device__ __forceinline__ float sqrt_apx(float v) { float r; asm("sqrt.approx.ftz.f32 %0, %1;" : "=f"(r) : "f"(v)); return r; }
__device__ __forceinline__ float rcp_apx(float v) { float r; asm("rcp.approx.ftz.f32 %0, %1;" : "=f"(r) : "f"(v)); return r; }
__device__ __forceinline__ uint32_t smem_u32(const void* p) { return (uint32_t)__cvta_generic_to_shared(p); }

constexpr int TAPB = 2944, TAPE = 928;
__device__ __align__(128) uint4 g_tap[DM * TAPB / 16];
#define XPAD 64
constexpr int XCP = SEQ + XPAD;
__device__ __align__(128) bf16 g_x1T[DM * XCP];
__device__ __align__(128) bf16 g_xcT[DM * XCP];
__device__ __align__(128) uint4 g_of[128 * 1280];
constexpr int WQ_STAGE = 240 * 128, WOB = 80 * 160;
__device__ __align__(128) uint4 g_wq[8 * 10 * WQ_STAGE / 16];
__device__ __align__(128) uint4 g_wo[64 * WOB / 16];
__device__ __align__(128) uint4 g_xb[128 * 240];
__device__ __align__(16) float g_csp[10 * 1920];
#define FSTR 32
__device__ __align__(128) float2 g_sum[2 * SEQ + 256 * FSTR];
__device__ __align__(16) bf16 g_piv[2 * SEQ];
__device__ __align__(128) bf16 g_yT[DM * XCP];
__device__ uint32_t g_epoch;
__device__ __align__(16) unsigned long long g_rstat[SEQ];
__device__ __align__(128) uint4 g_halo[640 * 148];
__device__ __forceinline__ unsigned long long tagw(uint32_t payload, uint32_t tag) { return ((unsigned long long)tag << 32) | payload; }
__device__ __forceinline__ ulonglong2 ld_tag2(const ulonglong2* p) {
    ulonglong2 v;
    asm volatile("ld.relaxed.gpu.global.v2.u64 {%0, %1}, [%2];" : "=l"(v.x), "=l"(v.y) : "l"(p) : "memory");
    return v;
}
__device__ __forceinline__ bool tag_ok(ulonglong2 v, uint32_t tag) { return (uint32_t)(v.x >> 32) == tag && (uint32_t)(v.y >> 32) == tag; }
__device__ __forceinline__ uint32_t ld_epoch() { uint32_t v; asm volatile("ld.relaxed.gpu.global.u32 %0, [%1];" : "=r"(v) : "l"(&g_epoch) : "memory"); return v + 1; }
constexpr int SPIN_MAX = 1 << 20;
__device__ __align__(128) uint32_t g_started[11 * 32];
__device__ __forceinline__ void sm_started(int slot) { asm volatile("red.relaxed.gpu.global.add.u32 [%0], 1;" ::"l"(g_started + slot) : "memory"); }
__device__ __forceinline__ void publish(int slot) {
    asm volatile("fence.proxy.async.global;" ::: "memory");
    asm volatile("red.release.gpu.global.add.u32 [%0], 1;" ::"l"(g_started + slot) : "memory");
}
__device__ __forceinline__ void await_all(int slot, uint32_t want) {
#pragma unroll 1
    for (int it = 0; it < SPIN_MAX; it++) {
        uint32_t v;
        asm volatile("ld.acquire.gpu.global.u32 %0, [%1];" : "=r"(v) : "l"(g_started + slot) : "memory");
        if (__all_sync(~0u, (int)(v - want) >= 0)) break;
        __nanosleep(50);
    }
    asm volatile("fence.proxy.async.global;" ::: "memory");
}
__device__ __noinline__ void sm_idle(int slot) {
    if (threadIdx.x != 288) return;
    asm volatile("fence.acq_rel.gpu;" ::: "memory");
    asm volatile("fence.proxy.async.global;" ::: "memory");
    sm_started(slot);
    const uint32_t want = ld_epoch() * gridDim.x;
    pdl_sync();
#pragma unroll 1
    for (int it = 0; it < SPIN_MAX; it++) {
        uint32_t v;
        asm volatile("ld.relaxed.gpu.global.u32 %0, [%1];" : "=r"(v) : "l"(g_started + slot) : "memory");
        if ((int)(v - want) >= 0) break;
        __nanosleep(100);
    }
}
struct TileTab { uint4 e[132]; };
__device__ __forceinline__ bool elect() {
    uint32_t p;
    asm volatile("{\n.reg .pred p;\nelect.sync _|p, 0xffffffff;\nselp.b32 %0, 1, 0, p;\n}" : "=r"(p));
    return p;
}
#define DBG_SYMS
#define TSTAMP(i)
#define TSTAMP1(i)
#define TSTAMP1T(i, t)
#define TSTAMP1X(i, t)
#define SPAN(k, i)
#define GSTAMP(arr, i)
#define TSTAMP2(i)
#define TSTAMP3(i)
#define TSTAMP4(i)
#define TSTAMPK(i, t)
#define TSTAMPC(i)
#define DBGC(i)
#define DBGV(i, v)
#define DBGCAL(i)

#define CSK(i)
#define CSK_END
#define CSA(i)
#define CSA_END
#define CST(i)
#define CST_END
#define CST_EXTRA 0
__device__ __forceinline__ void mma_bf16(float* d, uint32_t a0, uint32_t a1, uint32_t a2, uint32_t a3, uint32_t b0, uint32_t b1) {
    asm volatile("mma.sync.aligned.m16n8k16.row.col.f32.bf16.bf16.f32 {%0,%1,%2,%3}, {%4,%5,%6,%7}, {%8,%9}, {%0,%1,%2,%3};"
                 : "+f"(d[0]), "+f"(d[1]), "+f"(d[2]), "+f"(d[3]) : "r"(a0), "r"(a1), "r"(a2), "r"(a3), "r"(b0), "r"(b1));
}
__device__ __forceinline__ void mma_bf16_k8(float* d, uint32_t a0, uint32_t a1, uint32_t b0) {
    asm volatile("mma.sync.aligned.m16n8k8.row.col.f32.bf16.bf16.f32 {%0,%1,%2,%3}, {%4,%5}, {%6}, {%0,%1,%2,%3};"
                 : "+f"(d[0]), "+f"(d[1]), "+f"(d[2]), "+f"(d[3]) : "r"(a0), "r"(a1), "r"(b0));
}
__device__ __forceinline__ void ldsm_x4(uint32_t* r, uint32_t addr) {
    asm volatile("ldmatrix.sync.aligned.m8n8.x4.shared.b16 {%0,%1,%2,%3}, [%4];"
                 : "=r"(r[0]), "=r"(r[1]), "=r"(r[2]), "=r"(r[3]) : "r"(addr));
}

__device__ __forceinline__ void ldsm_x4_t(uint32_t* r, uint32_t addr) {
    asm volatile("ldmatrix.sync.aligned.m8n8.x4.trans.shared.b16 {%0,%1,%2,%3}, [%4];"
                 : "=r"(r[0]), "=r"(r[1]), "=r"(r[2]), "=r"(r[3]) : "r"(addr));
}
__device__ __forceinline__ void mbar_init(uint32_t bar, int count) { asm volatile("mbarrier.init.shared::cta.b64 [%0], %1;" ::"r"(bar), "r"(count)); }
__device__ __forceinline__ void mbar_arrive(uint32_t bar) { asm volatile("mbarrier.arrive.shared::cta.b64 _, [%0];" ::"r"(bar) : "memory"); }
__device__ __forceinline__ void mbar_wait(uint32_t bar, uint32_t parity) {
    asm volatile("{\n.reg .pred p;\nWAIT_LOOP:\n"
                 "mbarrier.try_wait.parity.shared::cta.b64 p, [%0], %1;\n"
                 "@p bra.uni WAIT_DONE;\nbra.uni WAIT_LOOP;\nWAIT_DONE:\n}" ::"r"(bar), "r"(parity) : "memory");
}

__device__ __forceinline__ void mbar_expect_tx(uint32_t bar, uint32_t bytes) {
    asm volatile("mbarrier.arrive.expect_tx.shared::cta.b64 _, [%0], %1;" ::"r"(bar), "r"(bytes) : "memory");
}
__device__ __forceinline__ void tma_load_2d(uint32_t dst, const void* tmap, int c0, int c1, uint32_t bar) {
    asm volatile("cp.async.bulk.tensor.2d.shared::cluster.global.mbarrier::complete_tx::bytes [%0], [%1, {%3, %4}], [%2];"
                 ::"r"(dst), "l"(tmap), "r"(bar), "r"(c0), "r"(c1) : "memory");
}
__device__ __forceinline__ void tma_load_3d(uint32_t dst, const void* tmap, int c0, int c1, int c2, uint32_t bar) {
    asm volatile("cp.async.bulk.tensor.3d.shared::cluster.global.mbarrier::complete_tx::bytes [%0], [%1, {%3, %4, %5}], [%2];"
                 ::"r"(dst), "l"(tmap), "r"(bar), "r"(c0), "r"(c1), "r"(c2) : "memory");
}
__device__ __forceinline__ void fence_async_smem() { asm volatile("fence.proxy.async.shared::cta;" ::: "memory"); }
__device__ __forceinline__ void bulk_load(uint32_t dst, const void* src, uint32_t bytes, uint32_t bar) {
    asm volatile("cp.async.bulk.shared::cluster.global.mbarrier::complete_tx::bytes [%0], [%1], %2, [%3];"
                 ::"r"(dst), "l"(src), "r"(bytes), "r"(bar) : "memory");
}
__device__ __forceinline__ void stsm_x4(uint32_t addr, uint32_t r0, uint32_t r1, uint32_t r2, uint32_t r3) {
    asm volatile("stmatrix.sync.aligned.m8n8.x4.shared.b16 [%0], {%1,%2,%3,%4};" ::"r"(addr), "r"(r0), "r"(r1), "r"(r2), "r"(r3) : "memory");
}
__device__ __forceinline__ void stsm_x4_t(uint32_t addr, uint32_t r0, uint32_t r1, uint32_t r2, uint32_t r3) {
    asm volatile("stmatrix.sync.aligned.m8n8.x4.trans.shared.b16 [%0], {%1,%2,%3,%4};" ::"r"(addr), "r"(r0), "r"(r1), "r"(r2), "r"(r3) : "memory");
}
__device__ __forceinline__ void prefetch_tmap(const void* tmap) { asm volatile("prefetch.tensormap [%0];" ::"l"(tmap) : "memory"); }

__device__ __forceinline__ float2 cexp_at(float wr2, float wi, float p) {
    float er;
    asm("ex2.approx.ftz.f32 %0, %1;" : "=f"(er) : "f"(wr2 * p));
    float th = wi * p;
    const float k = rintf(th * 0.15915494309189535f);
    th = fmaf(k, -6.2831854820251465f, th);
    th = fmaf(k, 1.7484555314695172e-7f, th);
    return make_float2(er * __cosf(th), er * __sinf(th));
}
__device__ __forceinline__ float2 cmul(float2 a, float2 b) {
    return make_float2(fmaf(a.x, b.x, -a.y * b.y), fmaf(a.x, b.y, a.y * b.x));
}
__device__ __forceinline__ float2 csqr(float2 a) { return make_float2(fmaf(a.x, a.x, -a.y * a.y), (a.x + a.x) * a.y); }
__device__ __forceinline__ uint32_t packh(float2 v) {
    uint32_t r;
    asm("cvt.rn.f16x2.f32 %0, %1, %2;" : "=r"(r) : "f"(v.y), "f"(v.x));
    return r;
}
__device__ __forceinline__ uint2 packr(float2 v) { return make_uint2(packh(v), packh(make_float2(-v.y, v.x))); }
__device__ __forceinline__ uint32_t hcmul(uint32_t a, uint2 b) {
    const __half2 x = *reinterpret_cast<const __half2*>(&a);
    const __half2 r = __hfma2(__high2half2(x), *reinterpret_cast<const __half2*>(&b.y), __hmul2(__low2half2(x), *reinterpret_cast<const __half2*>(&b.x)));
    return *reinterpret_cast<const uint32_t*>(&r);
}

struct Par { const bf16 *logA, *Aim, *Cre, *Cim, *logdt, *dsk; int layer, pad; const bf16* x; uint4 *sum, *wop, *of, *halo, *tap; float* csp; uint4* wq; const bf16 *wqkv, *wo; };
struct KgMaps { CUtensorMap q, o, t; };

__device__ __forceinline__ void bulk_prefetch(const void* p, uint32_t bytes) { asm volatile("cp.async.bulk.prefetch.L2.global [%0], %1;" ::"l"(p), "r"(bytes) : "memory"); }
__device__ __forceinline__ void bulk_store(void* dst, uint32_t src, uint32_t bytes) { asm volatile("cp.async.bulk.global.shared::cta.bulk_group [%0], [%1], %2;" ::"l"(dst), "r"(src), "r"(bytes) : "memory"); }
__device__ __forceinline__ void kgen_first(const Par& in, const KgMaps& tm, const uint32_t b0, const uint32_t wbar, const bool one) {
    const uint32_t blk = blockIdx.x, sec = (blk >= 40) + (blk >= 80), it = (blk >> 3) - 5 * sec, up = (blk >> 2) & 1, hi = blk >> 6;
    auto fetch = [&](int h) {
        if (blk < 120) asm volatile("cp.async.bulk.tensor.4d.shared::cluster.global.mbarrier::complete_tx::bytes [%0], [%1, {%3, %3, %4, %5}], [%2];"
                                    ::"r"(b0 + 10240 * h), "l"(&tm.q), "r"(wbar + 8 * h), "r"(0), "r"(sec * 40 + (blk & 7) * 5), "r"(2 * it + 10 * (up ^ h)) : "memory");
    };
    auto fetch_o = [&](int i) {
        asm volatile("cp.async.bulk.tensor.5d.shared::cluster.global.mbarrier::complete_tx::bytes [%0], [%1, {%3, %3, %4, %3, %5}], [%2];"
                     ::"r"(b0 + 20480 + i * 5120), "l"(&tm.o + i), "r"(wbar + 16), "r"(0), "r"((blk & 7) * 10 + (hi + i) * 4), "r"(((blk >> 3) & 7) * 5) : "memory");
    };
    if (one) {
#pragma unroll
        for (int i = 0; i < 3; i++) mbar_init(wbar + 8 * i, 1);
        asm volatile("fence.mbarrier_init.release.cluster;" ::: "memory");
        fetch(0);
    }
    __syncwarp();
    if (blk >> 20) __trap();
    if (one) {
        bulk_prefetch(in.wqkv + blk * 9600, 19200);
        fetch(1);
        bulk_prefetch(in.wo + blk * 3200, 6400);
        fetch_o(0);
        if (hi) fetch_o(1);
        mbar_expect_tx(wbar, 10240); mbar_expect_tx(wbar + 8, 10240); mbar_expect_tx(wbar + 16, 5120 + hi * 2560);
        bulk_prefetch(in.x + blk * 10240, 20480);
    }
}
__device__ __forceinline__ void kgen_side(const Par& in, const uint32_t b0, const uint32_t wbar) {
    const uint32_t blk = blockIdx.x, sec = (blk >= 40) + (blk >= 80), it = (blk >> 3) - 5 * sec, cg = (blk >> 3) & 7, hb = blk & 7;
    unsigned char* dst = reinterpret_cast<unsigned char*>(in.wq) + (hb * 10 + it) * WQ_STAGE + sec * 5120;
    if (blk < 120) {
        mbar_wait(wbar, 0);
        CSK(2);
        bulk_store(dst, b0, 5120); bulk_store(dst + 15360, b0 + 5120, 5120);
        mbar_wait(wbar + 8, 0);
        CSK(3);
        bulk_store(dst + 5 * WQ_STAGE, b0 + 10240, 5120); bulk_store(dst + 5 * WQ_STAGE + 15360, b0 + 15360, 5120);
        asm volatile("cp.async.bulk.commit_group;" ::: "memory");
        asm volatile("cp.async.bulk.wait_group 0;" ::: "memory");
        CSK(4);
        publish(96 + 32 * hb);
        CSK(5);
    }
    if (blk < 128) {
        mbar_wait(wbar + 16, 0);
        bulk_store(reinterpret_cast<unsigned char*>(in.wop) + (cg * 8 + (hb == cg ? 0 : hb + (hb < cg))) * WOB + (blk >> 6) * 5120, b0 + 20480, blk < 64 ? 5120 : 7680);
        asm volatile("cp.async.bulk.commit_group;" ::: "memory");
    }
}
__device__ __forceinline__ void kgen_sums(const Par& in, const uint32_t b0, const int h) {
    const int lane = threadIdx.x & 31, blk = blockIdx.x;
    if (blk < 120) {
        float cs[5][4] = {};
#pragma unroll
        for (int a = 0; a < 4; a++)
#pragma unroll
            for (int j = 0; j < 5; j++) {
                uint32_t w[4];
                ldsm_x4_t(w, b0 + h * 10240 + j * 1024 + ((lane >> 4) * 8 + (lane & 7)) * 32 + ((((lane >> 3) ^ (lane >> 2)) & 1) << 4) + (a >> 1) * 5120 + (a & 1) * 512);
                mma_bf16(cs[j], w[0], w[1], w[2], w[3], 0x3f803f80u, 0x3f803f80u);
            }
#pragma unroll
        for (int j = 0; j < 5; j++)
            if ((lane & 3) < 2) in.csp[(blk + 120 * h) * 80 + j * 16 + (lane >> 2) + 8 * (lane & 3)] = (lane & 3) ? cs[j][2] : cs[j][0];
    }
}
struct KgPar { uint32_t pw[4], ph[4], pdt, pdsk; };
__device__ __forceinline__ void kgen_load(const Par& in, const bf16* logA, const int w11, KgPar& k) {
    const uint32_t o = blockIdx.x * 480 + min(w11 * 48, w11 * 32 + 128), ow = o + (threadIdx.x & 31), oh = o + ow + (w11 < 8 ? 64 : 0);
    k.pdt = reinterpret_cast<const unsigned short*>(in.logdt)[ow / 96];
    k.pdsk = reinterpret_cast<const unsigned short*>(in.dsk)[ow / 96];
#pragma unroll
    for (int i = 0; i < 4; i++) {
        const bf16* p = i == 0 ? logA : i == 1 ? in.Aim : i == 2 ? in.Cre : in.Cim;
        k.pw[i] = reinterpret_cast<const uint32_t*>(p)[ow]; k.ph[i] = reinterpret_cast<const unsigned short*>(p)[oh];
    }
}
__device__ __forceinline__ void kgen_tables(const Par& in, uint4* tabs, const int w11, const KgPar& kp) {
    const int lane = threadIdx.x & 31, grp = min(w11 >> 1, 4), warp = w11 - 2 * grp;
    const int blk = blockIdx.x, d = blk * 5 + grp, tid = warp * 32 + lane;
    uint4* tab = tabs + grp * (2 * 256);
    const uint32_t *pw = kp.pw, *ph = kp.ph;
#pragma unroll
    for (int i = 0; i < 3; i++)
        if (i < 2 || w11 * 32 + lane < 36) asm volatile("st.global.v4.u32 [%0], {%1,%1,%1,%1};" ::"l"(in.halo + blk * 740 + w11 * 32 + lane + 352 * i), "r"(~0u));
    __syncwarp();
    if (w11 == 10) {
        if (lane < 16) in.sum[blk * 16 + lane] = make_uint4(0, 0, 0, 0);
        else if (lane < 20) reinterpret_cast<uint32_t*>(in.sum + 2048)[(blk * 4 + lane - 16) * FSTR] = 0;
    } else if (w11 > 1) asm volatile("bar.arrive 9, 352;" ::: "memory");
#pragma unroll
    for (int i = 0; i < 6; i++) tabs[w11 * 256 + 32 * i + lane] = make_uint4(0, 0, 0, 0);
    __syncwarp();
    CSK(1);
    const uint32_t tw = smem_u32(tabs) + w11 * 4096;
    const int g = lane >> 2, t = lane & 3;
    const int mt = lane >> 3, r = lane & 7;
    const uint32_t st1 = tw + mt * 1024 + r * 16, st2 = tw + (mt & 1) * 1024 + (mt >> 1) * 128 + ((r ^ (mt >> 1)) << 4), st3 = tw + 2048 + mt * 128 + ((r ^ mt) << 4);
    const uint32_t lda = tw + (mt & 1) * 1024 + r * 128 + (((mt >> 1) ^ r) << 4), ldb = tw + (mt >> 1) * 1024 + r * 128 + (((mt & 1) ^ r) << 4), ldc = tw + 2048 + r * 128 + ((mt ^ r) << 4);
    auto ldsm = [](uint32_t* v, uint32_t a) {
        asm volatile("ldmatrix.sync.aligned.m8n8.x4.shared.b16 {%0,%1,%2,%3}, [%4];" : "=r"(v[0]), "=r"(v[1]), "=r"(v[2]), "=r"(v[3]) : "r"(a) : "memory");
    };
    auto mma = [](float* c, const uint32_t* a, const uint32_t* b) {
        asm("mma.sync.aligned.m16n8k16.row.col.f32.f16.f16.f32 {%0,%1,%2,%3}, {%4,%5,%6,%7}, {%8,%9}, {%0,%1,%2,%3};"
            : "+f"(c[0]), "+f"(c[1]), "+f"(c[2]), "+f"(c[3]) : "r"(a[0]), "r"(a[1]), "r"(a[2]), "r"(a[3]), "r"(b[0]), "r"(b[1]));
    };
    asm volatile("st.shared.u32 [%0], %1;" ::"r"(tw + 3072), "r"(st1 ^ st2 ^ st3 ^ lda ^ ldb ^ ldc) : "memory");
    if (in.pad) __trap();
    const float dt = rbf(expf(__uint_as_float(kp.pdt << 16)));
    const uint32_t cm = __vmaxu2(__vmaxu2(pw[2] & 0x7fff7fffu, pw[3] & 0x7fff7fffu), __byte_perm(ph[2], ph[3], 0x5410) & 0x7fff7fffu);
    const int ex = min(max((int)(__float_as_uint(__uint_as_float(__reduce_max_sync(~0u, max(cm << 16, cm & 0xffff0000u))) * dt) >> 23), 20), 240);
    const float scale = __uint_as_float((uint32_t)(127 + 10 + 127 - ex) << 23), unscale = 2.0f * __uint_as_float((uint32_t)(ex - 10) << 23);
    float k2048 = 0.f;
    float acc[5][4] = {};
    uint32_t af[4][4] = {};
    auto rest = [&] {
        uint32_t b[4][4], c[8];
#pragma unroll
        for (int k = 0; k < 4; k++) {
            ldsm(b[k], ldb ^ (k << 5));
            if (!(k & 1)) ldsm(c + 2 * k, ldc ^ (k << 5));
        }
#pragma unroll
        for (int k = 0; k < 4; k++) { mma(acc[2], af[k], b[k]); mma(acc[3], af[k], b[k] + 2); mma(acc[4], af[k], c + 2 * k); }
    };
#pragma unroll 1
    for (uint32_t sel = 0x1076; sel < (grp < 4 ? 0x6000u : 0x4000u); sel += 0x2200) {
        rest();
        auto par = [&](int i) { return __uint_as_float(__byte_perm(pw[i], ph[i], sel)); };
        const float wr2 = -rbf(expf(par(0))) * dt * 1.4426950408889634f, wi = par(1) * dt;
        const float2 y1 = cexp_at(wr2, -wi, 1.f), w64 = cexp_at(wr2, wi, 64.f), y4 = csqr(csqr(y1)), z8 = csqr(make_float2(y4.x, -y4.y)), y128 = csqr(make_float2(w64.x, -w64.y));
        float2 h0 = make_float2(1.f, 0.f), g0 = make_float2(par(2) * dt * scale, -par(3) * dt * scale);
        const float2 v2 = csqr(y128), v3 = cmul(v2, y128), v4 = csqr(v2), v8 = csqr(v4), c8 = cmul(g0, v8);
        const uint2 z64 = packr(w64), v[8] = {make_uint2(packh(c8), 0u), packr(y128), packr(v2), packr(v3), packr(v4), packr(cmul(v4, y128)), packr(csqr(v3)), packr(cmul(v4, v3))};
        k2048 += fmaf(c8.x, v8.x, -c8.y * v8.y);
        uint32_t ge[4];
#pragma unroll
        for (int e = 0; e < 8; e++) {
            const uint32_t p = packh(h0), q = packh(g0);
            if (!(e & 1)) ge[e >> 1] = q;
            stsm_x4((st1 ^ (e << 4)) + e * 128, p, e ? hcmul(p, z64) : z64.x, q, hcmul(q, v[1]));
            if (e < 7) { h0 = e ? cmul(h0, z8) : z8; g0 = cmul(g0, y1); }
        }
        __syncwarp();
        uint32_t b[4][4];
#pragma unroll
        for (int k = 0; k < 4; k++) { ldsm(af[k], lda ^ (k << 5)); ldsm(b[k], (ldb ^ (k << 5)) + 2048); }
#pragma unroll
        for (int e = 0; e < 8; e += 2) {
            stsm_x4((st2 ^ (e << 4)) + e * 128, hcmul(ge[e & 3], v[2 + (e >> 2)]), hcmul(ge[0], v[4 + (e >> 1)]), hcmul(ge[(e & 3) + 1], v[2 + (e >> 2)]), hcmul(ge[2], v[4 + (e >> 1)]));
            if (!(e & 3)) stsm_x4((st3 ^ (e << 4)) + e * 128, e ? hcmul(v[0].x, v[e]) : v[0].x, hcmul(v[0].x, v[e + 1]), hcmul(v[0].x, v[e + 2]), hcmul(v[0].x, v[e + 3]));
            mma(acc[0], af[e >> 1], b[e >> 1]);
            mma(acc[1], af[e >> 1], b[e >> 1] + 2);
        }
        __syncwarp();
        if (sel == 0x1076) CSK(3);
    }
    rest();
#pragma unroll
    for (int e = 0; e < 5; e++) k2048 += __shfl_xor_sync(~0u, k2048, 1 << e);
    {
        float* Pp = reinterpret_cast<float*>(tab + warp * 256);
        auto sw = [](int i) { return i ^ ((i >> 2) & 24); };
#pragma unroll
        for (int h = 0; h < 2; h++) {
            const int b = g + 8 * h;
            *reinterpret_cast<float2*>(Pp + sw(8 * b + 2 * t)) = make_float2(acc[0][2 * h] * unscale, acc[0][2 * h + 1] * unscale);
            *reinterpret_cast<float2*>(Pp + 128 + sw(8 * b + 2 * t)) = make_float2(acc[1][2 * h] * unscale, acc[1][2 * h + 1] * unscale);
            *reinterpret_cast<float2*>(Pp + 256 + sw(4 * b + 2 * (t & 1) + 64 * (t >> 1))) = make_float2(acc[2][2 * h] * unscale, acc[2][2 * h + 1] * unscale);
            *reinterpret_cast<float2*>(Pp + 384 + sw(2 * b + 32 * t)) = make_float2(acc[3][2 * h] * unscale, acc[3][2 * h + 1] * unscale);
            Pp[512 + sw(b + 32 * t)] = acc[4][2 * h] * unscale;
            Pp[512 + sw(b + 32 * t + 16)] = acc[4][2 * h + 1] * unscale;
        }
        if (lane == 0) Pp[640] = k2048 * unscale;
    }
    CSK(4);
    asm volatile("bar.sync %0, %1;" ::"r"(grp + 4), "r"(grp < 4 ? 64 : 96) : "memory");
    if (warp == 2) return;
    const float* Kp = reinterpret_cast<const float*>(tab);
    auto ksum = [&](int i) -> float { return rbf(Kp[i] + Kp[1024 + i] + (grp < 4 ? 0.f : Kp[2048 + i])); };
    auto ksum2 = [&](int q) -> float2 {
        q ^= (q >> 2) & 12;
        const float2 a = reinterpret_cast<const float2*>(Kp)[q], b = reinterpret_cast<const float2*>(Kp)[512 + q];
        const float2 c = grp < 4 ? make_float2(0.f, 0.f) : reinterpret_cast<const float2*>(Kp)[1024 + q];
        return make_float2(a.x + b.x + c.x, a.y + b.y + c.y);
    };
    {
        uint2* W2 = reinterpret_cast<uint2*>(in.tap + d * (TAPB / 16)) + 8;
        uint2* E4 = W2 + (TAPE - 64) / 8;
        float2 v = ksum2(64 * warp + lane), z = ksum2(64 * warp + 32 + lane), y = ksum2(128 + tid);
        const int q = (96 + tid) ^ (((96 + tid) >> 2) & 6);
        const float4 ua = reinterpret_cast<const float4*>(Kp)[q], uc = reinterpret_cast<const float4*>(Kp)[256 + q], ud = grp < 4 ? make_float4(0.f, 0.f, 0.f, 0.f) : reinterpret_cast<const float4*>(Kp)[512 + q];
        const float4 ub = make_float4(uc.x + ud.x, uc.y + ud.y, uc.z + ud.z, uc.w + ud.w);
        const float s1 = ksum(tid == 31 ? 336 : lane ? 384 : 103), s2 = ksum(tid == 31 ? 512 : tid ? 640 : 231);
        if (tid == 0) v.x += __uint_as_float(kp.pdsk << 16);
        if (tid == 63) y.y -= s1;
        const uint32_t lo = pack2(v.x, v.y), hi = pack2(z.x, z.y), tp = pack2(y.x, y.y);
        uint32_t nl = __shfl_sync(~0u, lo, lane - 1), nh = __shfl_sync(~0u, lane == 31 ? lo : hi, lane - 1), nt = __shfl_sync(~0u, tp, lane + 1);
        if (lane == 0) nl = warp ? __float_as_uint(s1) : 0u;
        if (lane == 31) nt = warp ? 0u : __float_as_uint(s1) >> 16;
        W2[64 * warp + lane] = make_uint2(__byte_perm(lo, nl, 0x7610), __byte_perm(lo, 0, 0x1032));
        W2[64 * warp + lane + 32] = make_uint2(__byte_perm(hi, nh, 0x7610), __byte_perm(hi, 0, 0x1032));
        reinterpret_cast<uint4*>(W2)[64 + tid] = make_uint4(__byte_perm(tp, __float_as_uint(s2), tid ? 0x1010 : 0x7610), __byte_perm(tp, 0, 0x1010), __byte_perm(tp, 0, 0x1032), __byte_perm(nt, tp, 0x7610));
        E4[(tid < 32 ? 159 : 209 - 32) + tid] = make_uint2(pack2(ua.x + ub.x, ua.y + ub.y), pack2(ua.z + ub.z, ua.w + ub.w - (tid == 31 ? s2 : 0.f)));
        if (tid == 63) E4[241] = make_uint2(__float_as_uint(s2) >> 16, 0u);
    }
    CSK(5);
    SPAN(0, 3);
}

#define CV_SLEEP 40
#define CV_LD "ld.relaxed.gpu.global"
#define CV_NL 1
#define CV_D2 3
#define CV_PDH 12
#define CV_PDF 4
#define CV_HAND 7
constexpr int CV_CPB = 5;
constexpr int CV_THREADS = 512;
constexpr int UPADF = 128;
constexpr int ULEN = UPADF + SEQ;
constexpr int XLEN = XCP;
constexpr int BX_5 = 0, BX_3 = 3264, BX_9 = 6528, BX_7 = 8960, BX_LEN = 11392;
constexpr int CV_SM_U = 0;
constexpr int CV_SM_T = CV_CPB * ULEN * 2;
constexpr int CV_SM_B = CV_SM_T + CV_CPB * TAPB;
constexpr int CV_SM_X = CV_SM_B + CV_CPB * BX_LEN;
constexpr int CV_SM_Y = (CV_SM_X + CV_CPB * XLEN * 2 + 127) & ~127;
constexpr int CV_SM_CNT = CV_SM_Y + CV_CPB * 8192;
constexpr int CV_SM_O = CV_SM_CNT + 128;
constexpr int CV_SMEM = CV_SM_O + 20480 + CST_EXTRA;
static_assert(ULEN % 128 == 0 && CV_SM_B % 128 == 0 && CV_SM_CNT % 128 == 0, "layout");

__device__ __forceinline__ uint32_t sub2(uint32_t x, uint32_t m) {
    const __nv_bfloat162 d = __hsub2(*reinterpret_cast<const __nv_bfloat162*>(&x), *reinterpret_cast<const __nv_bfloat162*>(&m));
    return *reinterpret_cast<const uint32_t*>(&d);
}
__device__ __forceinline__ uint32_t add2(uint32_t x, uint32_t y) {
    const __nv_bfloat162 d = __hadd2_rn(*reinterpret_cast<const __nv_bfloat162*>(&x), *reinterpret_cast<const __nv_bfloat162*>(&y));
    return *reinterpret_cast<const uint32_t*>(&d);
}
__device__ __forceinline__ void wgmma_fence() { asm volatile("wgmma.fence.sync.aligned;" ::: "memory"); }
__device__ __forceinline__ void wgmma_commit() { asm volatile("wgmma.commit_group.sync.aligned;" ::: "memory"); }
template <int N> __device__ __forceinline__ void wgmma_wait() { asm volatile("wgmma.wait_group.sync.aligned %0;" ::"n"(N) : "memory"); }
__device__ __forceinline__ uint64_t make_desc(uint32_t addr, uint32_t lbo, uint32_t sbo, uint32_t mode) {
    return (uint64_t)((addr & 0x3FFFF) >> 4) | ((uint64_t)(lbo >> 4) << 16) | ((uint64_t)(sbo >> 4) << 32) | ((uint64_t)mode << 62);
}
__device__ __forceinline__ void wgmma_rs128(float (&d)[64], uint2 hi, uint2 lo, uint64_t db, int acc) {
    asm volatile("{\n.reg .pred p;\nsetp.ne.b32 p, %69, 0;\nwgmma.mma_async.sync.aligned.m64n128k16.f32.bf16.bf16 {%0,%1,%2,%3,%4,%5,%6,%7,%8,%9,%10,%11,%12,%13,%14,%15,%16,%17,%18,%19,%20,%21,%22,%23,%24,%25,%26,%27,%28,%29,%30,%31,%32,%33,%34,%35,%36,%37,%38,%39,%40,%41,%42,%43,%44,%45,%46,%47,%48,%49,%50,%51,%52,%53,%54,%55,%56,%57,%58,%59,%60,%61,%62,%63}, {%64,%65,%66,%67}, %68, p, 1, 1, 0;\n}"
                 : "+f"(d[0]), "+f"(d[1]), "+f"(d[2]), "+f"(d[3]), "+f"(d[4]), "+f"(d[5]), "+f"(d[6]), "+f"(d[7]), "+f"(d[8]), "+f"(d[9]), "+f"(d[10]), "+f"(d[11]), "+f"(d[12]), "+f"(d[13]), "+f"(d[14]), "+f"(d[15]), "+f"(d[16]), "+f"(d[17]), "+f"(d[18]), "+f"(d[19]), "+f"(d[20]), "+f"(d[21]), "+f"(d[22]), "+f"(d[23]), "+f"(d[24]), "+f"(d[25]), "+f"(d[26]), "+f"(d[27]), "+f"(d[28]), "+f"(d[29]), "+f"(d[30]), "+f"(d[31]), "+f"(d[32]), "+f"(d[33]), "+f"(d[34]), "+f"(d[35]), "+f"(d[36]), "+f"(d[37]), "+f"(d[38]), "+f"(d[39]), "+f"(d[40]), "+f"(d[41]), "+f"(d[42]), "+f"(d[43]), "+f"(d[44]), "+f"(d[45]), "+f"(d[46]), "+f"(d[47]), "+f"(d[48]), "+f"(d[49]), "+f"(d[50]), "+f"(d[51]), "+f"(d[52]), "+f"(d[53]), "+f"(d[54]), "+f"(d[55]), "+f"(d[56]), "+f"(d[57]), "+f"(d[58]), "+f"(d[59]), "+f"(d[60]), "+f"(d[61]), "+f"(d[62]), "+f"(d[63])
                 : "r"(hi.x), "r"(hi.y), "r"(lo.x), "r"(lo.y), "l"(db), "r"(acc));
}
template <int V> struct Int { __device__ constexpr operator int() const { return V; } };
__device__ __forceinline__ void sts4(uint32_t a, const uint32_t* v) { asm volatile("st.shared.v4.u32 [%0], {%1,%2,%3,%4};" ::"r"(a), "r"(v[0]), "r"(v[1]), "r"(v[2]), "r"(v[3]) : "memory"); }
__device__ __forceinline__ uint32_t lds1(uint32_t a) { uint32_t v; asm volatile("ld.shared.u32 %0, [%1];" : "=r"(v) : "r"(a) : "memory"); return v; }
__device__ __forceinline__ uint32_t lds1v(uint32_t a) { uint32_t v; asm volatile("ld.volatile.shared.u32 %0, [%1];" : "=r"(v) : "r"(a) : "memory"); return v; }
__device__ __forceinline__ uint4 lds4(uint32_t a) { uint4 v; asm volatile("ld.shared.v4.u32 {%0,%1,%2,%3}, [%4];" : "=r"(v.x), "=r"(v.y), "=r"(v.z), "=r"(v.w) : "r"(a) : "memory"); return v; }
__device__ __forceinline__ uint4 ldx(uint32_t a) {
    uint4 v;
    asm volatile("ld.shared.v2.u32 {%0,%1}, [%4];\nld.shared.v2.u32 {%2,%3}, [%4+128];" : "=r"(v.x), "=r"(v.y), "=r"(v.z), "=r"(v.w) : "r"(a) : "memory");
    return v;
}
__device__ __forceinline__ void cv_store(unsigned char* p, uint4 x, uint4 y) {
    asm volatile("st.relaxed.gpu.global.v2.u32 [%0], {%1,%2};" ::"l"(p), "r"(add2(x.x, __byte_perm(y.x, y.y, 0x5410))), "r"(add2(x.y, __byte_perm(y.z, y.w, 0x5410))) : "memory");
    asm volatile("st.relaxed.gpu.global.v2.u32 [%0], {%1,%2};" ::"l"(p + 128), "r"(add2(x.z, __byte_perm(y.x, y.y, 0x7632))), "r"(add2(x.w, __byte_perm(y.z, y.w, 0x7632))) : "memory");
}
__device__ __forceinline__ int usw(int ch) { return ch ^ ((ch >> 3) & 1); }
__global__ void __launch_bounds__(CV_THREADS, 1) conv_kernel(int layer, const uint4* __restrict__ piv, const float4* __restrict__ sum, const bf16* __restrict__ x1T,
                                                             bf16* __restrict__ dst, const uint4* __restrict__ tap, const __grid_constant__ CUtensorMap tmOut) {
    extern __shared__ __align__(1024) unsigned char sm[];
    SPAN(3 + 4 * layer, 0);
    bf16* Us = reinterpret_cast<bf16*>(sm + CV_SM_U);
    bf16* Xs = reinterpret_cast<bf16*>(sm + CV_SM_X);
#define CV_IDX int tid; asm volatile("mov.u32 %0, %tid.x;" : "=r"(tid)); const int lane = tid & 31, warp = __shfl_sync(~0u, tid >> 5, 0);
    const int d0 = blockIdx.x * CV_CPB, tile = blockIdx.x; (void)tile;
    const uint32_t cnt = smem_u32(sm + CV_SM_CNT);
    struct Lc { uint32_t a4, a8, uc, ud, y, e4, en, sp, ss; int go; };
    auto lane_consts = [&](int lane, int c) {
        const int mat = lane >> 3, r = lane & 7, g = lane >> 2, ti = lane & 3, e = g - 2 * ti;
        const int j2 = 13 + (r ^ 1) + 8 * (mat >> 1), j3 = j2 + 2, i0 = 8 * (mat & 1);
        const uint32_t sb = smem_u32(sm), oc = sb + usw(16 * (mat >> 1) + 2 * r + (mat & 1)) * 16;
        const Lc l = {sb + CV_SM_B + c * BX_LEN + ((j2 & 1) ? BX_3 + (4 * j2 + i0 + 84) * 2 : BX_5 + (4 * j2 + i0 + 80) * 2),
                      sb + CV_SM_B + c * BX_LEN + ((j3 & 1) ? BX_7 : BX_9) + (8 * j3 + i0 + 136) * 2,
                      oc + CV_SM_U + (c * ULEN + UPADF) * 2, sb + CV_SM_U + (c * ULEN + UPADF) * 2 + usw(16 * mat + 2 * r + 2) * 16, oc + CV_SM_Y + c * 8192,
                      sb + CV_SM_T + c * TAPB + TAPE + (307 + 2 * g - ti) * 4, sb + CV_SM_T + c * TAPB + (528 + e) * 4,
                      e == -5 ? 0x4410u : e == -4 ? 0x1044u : 0x4444u, e == 3 ? 0x4410u : e == 4 ? 0x1044u : 0x4444u,
                      c * XCP * 2 + (lane >> 4) * 256 + (lane & 15) * 8};
        asm volatile("st.shared.u32 [%0], %1;" ::"r"(sb + CV_SM_CNT + 120), "r"(l.y ^ l.a4 ^ l.a8 ^ l.uc ^ l.ud ^ l.e4 ^ l.en ^ l.sp ^ l.ss ^ l.go) : "memory");
        return l;
    };
    unsigned char* const dq = reinterpret_cast<unsigned char*>(dst + (size_t)d0 * XCP);
    auto far = [&](auto T0_, const auto& seq, const Lc& lc, int c, int lane, const uint2 (&f)[20], uint32_t kk) {
        constexpr int T0 = T0_, T1 = T0 + 6, TC = T0 > 7 ? T0 : 7, NS = sizeof(seq) / sizeof(seq[0]), PD = T0 > 7 ? CV_PDH : CV_PDF;
        uint32_t bq[28], yw[4], yz[4], P, S;
        uint4 xv, yv;
        asm("prmt.b32 %0, %1, 0, %2;" : "=r"(P) : "r"(kk), "r"(lc.sp));
        asm("prmt.b32 %0, %1, 0, %2;" : "=r"(S) : "r"(kk), "r"(lc.ss));
#pragma unroll
        for (int k = 0; 2 * k < T1 - TC + 4; k++) ldsm_x4(bq + 4 * k, lc.uc + (TC - 8) * 256 + 512 * k);
#pragma unroll
        for (int k = 0; 4 * k < T1 - TC; k++) ldsm_x4(bq + 20 + 4 * k, lc.ud + (TC - 8) * 256 + 1024 * k);
        CST(3);
        mbar_wait(cnt + 8 * c, 0);
        mbar_wait(cnt + 40, 0);
        CST(4);
        float acc[6][4] = {};
        uint32_t a[PD + 1][4];
#pragma unroll
        for (int i = -PD; i < NS + 3; i++) {
            if (i + PD < NS) ldsm_x4_t(a[(i + PD) % (PD + 1)], seq[i + PD] < 32 ? lc.a4 + (seq[i + PD] - 2) * 128 : lc.a8 + (seq[i + PD] - 34) * 256);
            if (i < 0) continue;
#pragma unroll
            for (int T = T0; T < T1; T++) {
                if (i >= NS) break;
                const int ee = seq[i] < 32 ? 2 * T - 6 - seq[i] : T + 35 - seq[i];
                if (i == 0 && T >= TC) mma_bf16(acc[T - T0], P, 0u, S, P, bq[2 * (T - TC)], bq[2 * (T - TC) + 1]);
                if (i == 1 && T >= TC) mma_bf16_k8(acc[T - T0], 0u, S, bq[20 + T - TC]);
                if (i == (T >= TC ? 2 : 0)) mma_bf16(acc[T - T0], f[19].x, 0u, f[19].y, f[19].x, bq[2 * (T - TC + 4)], bq[2 * (T - TC + 4) + 1]);
                if (seq[i] < 32 ? ee >= 0 && ee <= 9 : ee >= 10) mma_bf16(acc[T - T0], a[i % (PD + 1)][0], a[i % (PD + 1)][1], a[i % (PD + 1)][2], a[i % (PD + 1)][3], f[ee].x, f[ee].y);
            }
#pragma unroll
            for (int k = 0; k < 3; k++) {
                const int o = 256 * T0 + 512 * k;
                auto at = [&](int d) { return i - d >= 0 && i - d < NS && seq[i - d < 0 ? 0 : i - d < NS ? i - d : 0] == 2 * T0 + 4 * k - 4; };
                if (at(CV_D2)) {
                    cv_store(dq + lc.go + o, xv, yv);
                    if (layer > 19 - 2 * k) __trap();
                }
                if (at(-2)) { ldsm_x4_t(yw, lc.y + o); ldsm_x4_t(yz, lc.y + 3584 + o); }
                if (at(1)) {
#pragma unroll
                    for (int q = 0; q < 4; q++) yw[q] = add2(add2(yw[q], yz[q]), pack2(acc[2 * k + (q >> 1)][2 * (q & 1)], acc[2 * k + (q >> 1)][2 * (q & 1) + 1]));
                    stsm_x4_t(lc.y + o, yw[0], yw[1], yw[2], yw[3]);
                    xv = ldx(smem_u32(Xs) + lc.go + o);
                    __syncwarp();
                    yv = lds4(smem_u32(sm + CV_SM_Y) + c * 8192 + o + usw(lane) * 16);
                    if (layer > 20 - 2 * k) __trap();
                    if (k == 2) CST(6);
                }
            }
        }
    };
    TSTAMP1X(9, 256);
    if (threadIdx.x >= 256) {
        if (threadIdx.x < 288 && elect()) {
            mbar_init(cnt + 48, 1);
            asm volatile("fence.mbarrier_init.release.cluster;" ::: "memory");
            bulk_load(smem_u32(sm + CV_SM_T), tap + d0 * (TAPB / 16), CV_CPB * TAPB, cnt + 48);
            mbar_expect_tx(cnt + 48, CV_CPB * TAPB);
        }
        CV_IDX
        const int wgu = (warp >> 2) & 1, g = lane >> 2, ti = lane & 3;
        CST(1);
        if (warp > 8 && elect()) {
            if (warp < 15) mbar_init(cnt + 8 * (warp - 9), warp == 14 ? 8 : 4);
            else if (layer) prefetch_tmap(&tmOut);
        }
        if (warp < 13 && lane < 17 - (warp == 12)) {
            const int off = warp == 12 ? CV_SM_U : CV_SM_B + (warp == 11 ? BX_7 : (warp - 8) * BX_3), str = warp == 12 ? ULEN * 2 : BX_LEN;
#pragma unroll
            for (int c = 0; c < CV_CPB; c++) *reinterpret_cast<uint4*>(sm + off + c * str + 16 * lane) = make_uint4(0, 0, 0, 0);
        }
        fence_async_smem();
        asm volatile("bar.arrive 3, 512;" ::: "memory");
        asm volatile("bar.sync 1, 256;" ::: "memory");
        TSTAMP1X(10, 256);
        asm volatile("setmaxnreg.inc.sync.aligned.u32 168;");
        const uint32_t Tc = smem_u32(sm + CV_SM_T) + (16 + 128 * (warp & 2) + 8 * (warp & 1) + g - 2 * ti) * 4;
        uint2 fa[8][2], fn[8][2];
        auto near_taps = [&](uint2 (&f)[8][2], int c) {
#pragma unroll
            for (int m = 0; m < 16; m++) f[m >> 1][m & 1] = make_uint2(lds1v(Tc + c * TAPB + 64 * (m >> 1) - 32 * (m & 1)), lds1v(Tc + c * TAPB + 64 * (m >> 1) - 32 * (m & 1) + 512));
        };
        CST(6);
        mbar_wait(cnt + 48, 0);
        TSTAMP1X(11, 256); CST(5);
        near_taps(fa, 3 * wgu);
        near_taps(fn, 2 - wgu);
        const int hc = wgu ? warp & 3 : 4;
        const Lc lc = lane_consts(lane, hc);
        TSTAMP1X(12, 256); CST(0);
        uint32_t ya = smem_u32(sm + CV_SM_Y) + wgu * 8192 + (warp & 2) * 2048 + usw(2 * lane + (warp & 1)) * 16;
        uint64_t db = make_desc(smem_u32(Us + wgu * ULEN + UPADF), 16, 256, 3);
        if (wgu) { asm volatile("bar.sync 6, 384;" ::: "memory"); fence_async_smem(); }
        int c = wgu;
        auto chain = [&](const uint2 (&f)[8][2], auto&& meanwhile) {
            float acc[64];
            asm volatile("bar.sync %0, %1;" ::"r"(c ? 4 + wgu : 2), "r"(c ? 256 : 384) : "memory");
            TSTAMPC(1 + 3 * c);
            if (c < 2) CST(7);
            if (c == 0) fence_async_smem();
            wgmma_fence();
#pragma unroll
            for (int m = 0; m < 8; m++) {
                wgmma_rs128(acc, f[m][0], f[m][1], db - (uint64_t)(2 * m), m);
                if (m == CV_HAND && c < 4) asm volatile("bar.arrive %0, 256;" ::"r"(5 - wgu) : "memory");
            }
            wgmma_commit();
            asm volatile("griddepcontrol.launch_dependents;" ::: "memory");
            TSTAMPC(2 + 3 * c); CST(13 + (c >> 1));
            meanwhile();
            wgmma_wait<0>();
            TSTAMPC(3 + 3 * c); CST(10 + (c >> 1));
            uint32_t w[16];
#pragma unroll
            for (int j = 0; j < 16; j++) w[j] = j ? pack2(acc[4 * j] + acc[4 * j - 2], acc[4 * j + 1] + acc[4 * j - 1]) : pack2(acc[0], acc[1]);
#pragma unroll
            for (int j = 0; j < 16; j += 4) stsm_x4_t(ya + 256 * j, w[j], w[j + 1], w[j + 2], w[j + 3]);
            __syncwarp();
            if (lane == 0) mbar_arrive(cnt + 8 * c);
            c += 2; ya += 16384; db += ULEN / 4;
        };
        const uint32_t e4 = lc.e4, e8 = e4 + 428 - 4 * g;
        uint2 fl[4];
        uint32_t kk;
#pragma unroll 1
        for (;;) {
            if (c != 1) chain(fa, [&] {
                if (c == 3 || warp + c == 12) {
#pragma unroll
                    for (int k = 0; k < 19; k++) (k < 16 ? fn[(k >> 1) & 7][k & 1] : fl[k & 3]) = make_uint2(lds1(k < 10 ? e4 + 32 * k + 16 : e8 + 32 * k - 304), lds1(k < 10 ? e4 + 32 * k : e8 + 32 * k - 320));
                    fl[3] = make_uint2(lds1(lc.en), lds1(lc.en - 32));
                    kk = lds1(smem_u32(sm + CV_SM_T) + TAPB * hc + TAPE + 1672);
                }
            });
            if (c > 4) break;
            if (c == 2) { asm volatile("bar.sync 7, 384;" ::: "memory"); fence_async_smem(); }
            chain(fn, [&] { if (c == 2) near_taps(fa, 4); });
        }
        TSTAMP1X(6, 256); CST(2);
        if (wgu || warp == 8) {
            constexpr int seq[29] = {5, 6, 32, 7, 33, 8, 34, 9, 35, 10, 36, 11, 12, 13, 14, 15, 16, 17, 37, 18, 38, 19, 20, 21, 39, 22, 40, 23, 24};
            uint2 f[20];
#pragma unroll
            for (int k = 0; k < 20; k++) f[k] = k < 16 ? fn[(k >> 1) & 7][k & 1] : fl[k & 3];
            far(Int<10>(), seq, lc, hc, lane, f, kk);
        }
    } else {
        asm volatile("setmaxnreg.dec.sync.aligned.u32 88;");
        CV_IDX
        CST(5);
        const uint4* ppv = piv + tid;
        const float4* psv = sum + tid;
        const uint2* pxv = reinterpret_cast<const uint2*>(x1T + (size_t)d0 * XCP) + (tid >> 4) * 32 + (tid & 15);
        asm volatile("st.shared.u64 [%0], %1;" ::"r"(smem_u32(sm + CV_SM_O) + tid * 16), "l"((uint64_t)ppv ^ (uint64_t)psv ^ (uint64_t)pxv) : "memory");
        const int tc = (0x04302100 >> (4 * warp)) & 7;
        const Lc lc = lane_consts(lane, tc);
        pdl_sync();
        SPAN(3 + 4 * layer, 1);
        TSTAMP(0); CST(0);
        if (tid == 0) TSTAMPC(0);
        if (threadIdx.x == 0) { GSTAMP(g_tim, 15); }
        float4 sv[4];
        uint4 pv;
#pragma unroll
        for (int k = 0; k < 4; k++)
            asm volatile(CV_LD ".v4.f32 {%0,%1,%2,%3}, [%4];" : "=f"(sv[k].x), "=f"(sv[k].y), "=f"(sv[k].z), "=f"(sv[k].w) : "l"(psv + 256 * k) : "memory");
        asm volatile(CV_LD ".v4.u32 {%0,%1,%2,%3}, [%4];" : "=r"(pv.x), "=r"(pv.y), "=r"(pv.z), "=r"(pv.w) : "l"(ppv) : "memory");
        uint2 xe[CV_CPB], xo[CV_CPB];
#pragma unroll
        for (int c = 0; c < CV_NL; c++) {
            asm volatile(CV_LD ".v2.u32 {%0,%1}, [%2];" : "=r"(xe[c].x), "=r"(xe[c].y) : "l"(pxv + c * (XCP / 4)) : "memory");
            asm volatile(CV_LD ".v2.u32 {%0,%1}, [%2];" : "=r"(xo[c].x), "=r"(xo[c].y) : "l"(pxv + c * (XCP / 4) + 16) : "memory");
        }
#define CV_XD 300
#define CV_XW 0
        if (warp == CV_XW) {
            if (elect()) {
                const uint32_t c0 = clock();
                mbar_init(cnt + 56, 1);
                asm volatile("fence.mbarrier_init.release.cluster;" ::: "memory");
                mbar_expect_tx(cnt + 56, CV_CPB * 4096);
                while (clock() - c0 < CV_XD) ;
#pragma unroll
                for (int c = CV_NL; c < CV_CPB + CV_NL; c++) bulk_load(smem_u32(Xs + (c % CV_CPB) * XLEN), x1T + (size_t)(d0 + c % CV_CPB) * XCP, 4096, cnt + 56);
            }
            __syncwarp();
            CST(15);
        }
        constexpr float idm = 1.0f / DM;
        uint32_t mw[4];
        float rs[8];
#pragma unroll
        for (int k = 0; k < 4; k++) {
            const uint32_t pw = k == 0 ? pv.x : k == 1 ? pv.y : k == 2 ? pv.z : pv.w;
            mw[k] = pack2(fmaf(sv[k].x, idm, __uint_as_float(pw << 16)), fmaf(sv[k].z, idm, __uint_as_float(pw & 0xffff0000u)));
            uint32_t vr;
            asm("cvt.rn.relu.bf16x2.f32 %0, %1, %2;" : "=r"(vr) : "f"(fmaf(sv[k].z * -idm, sv[k].z, sv[k].w) * idm), "f"(fmaf(sv[k].x * -idm, sv[k].x, sv[k].y) * idm));
            const uint32_t ve = pack2(__uint_as_float(vr << 16) + 1e-5f, __uint_as_float(vr & 0xffff0000u) + 1e-5f);
            const uint32_t sd = pack2(sqrt_apx(__uint_as_float(ve << 16)), sqrt_apx(__uint_as_float(ve & 0xffff0000u)));
            rs[2 * k] = rcp_apx(__uint_as_float(sd << 16)); rs[2 * k + 1] = rcp_apx(__uint_as_float(sd & 0xffff0000u));
        }
        if (rs[0] != 123.f) TSTAMP(13);
        const uint32_t ua = smem_u32(Us) + usw(tid + UPADF / 8) * 16;
        uint32_t uw[CV_CPB][4];
#pragma unroll
        for (int c = 0; c < CV_CPB; c++) {
            if (c == CV_NL) {
                if (warp == CV_XW) { mbar_wait(cnt + 56, 0); CST(7); }
                asm volatile("bar.sync 10, 256;" ::: "memory");
            }
            if (c == 1 || c == 2) {
#pragma unroll
                for (int k = c; k < (c == 1 ? 2 : CV_CPB); k++) {
 const uint4 v = ldx(smem_u32(Xs + k * XLEN) + (tid >> 4) * 256 + (tid & 15) * 8); xe[k] = make_uint2(v.x, v.y); xo[k] = make_uint2(v.z, v.w); }
            }
            const uint32_t e0 = sub2(xe[c].x, mw[0]), e1 = sub2(xe[c].y, mw[1]), o0 = sub2(xo[c].x, mw[2]), o1 = sub2(xo[c].y, mw[3]);
            uw[c][0] = pack2(__uint_as_float(e0 << 16) * rs[0], __uint_as_float(o0 << 16) * rs[4]); uw[c][1] = pack2(__uint_as_float(e0 & 0xffff0000u) * rs[1], __uint_as_float(o0 & 0xffff0000u) * rs[5]);
            uw[c][2] = pack2(__uint_as_float(e1 << 16) * rs[2], __uint_as_float(o1 << 16) * rs[6]); uw[c][3] = pack2(__uint_as_float(e1 & 0xffff0000u) * rs[3], __uint_as_float(o1 & 0xffff0000u) * rs[7]);
            asm volatile("st.shared.v4.u32 [%0], {%1,%2,%3,%4};" ::"r"(ua + c * ULEN * 2), "r"(uw[c][0]), "r"(uw[c][1]), "r"(uw[c][2]), "r"(uw[c][3]) : "memory");
            if (c < 2) {
                asm volatile("bar.arrive %0, 384;" ::"r"(2 + 4 * c) : "memory");
                if (layer > 29 - c) __trap();
                CST(11 + c);
            }
        }
        asm volatile("bar.arrive 7, 384;" ::: "memory");
        asm volatile("bar.sync 3, 512;" ::: "memory");
        TSTAMP(1); CST(1);
        {
            auto box = [&](auto c0, auto c1, int chunk, int cb, bool full) {
                const uint32_t ea = smem_u32(Us + cb * ULEN) + usw(chunk + UPADF / 8 + (lane ? 1 : -1)) * 16, bx = smem_u32(sm + CV_SM_B + cb * BX_LEN) + chunk * 16;
                uint32_t lo[CV_CPB][4], hi[CV_CPB][2];
#pragma unroll
                for (int c = c0; c < c1; c++) {
                    lo[c][0] = 0;
#pragma unroll
                    for (int k = 1; k < 4; k++) lo[c][k] = __shfl_up_sync(~0u, uw[c][k], 1);
#pragma unroll
                    for (int k = 0; k < 2; k++) hi[c][k] = __shfl_down_sync(~0u, uw[c][k], 1);
                }
#pragma unroll
                for (int c = c0; c < c1; c++)
                    asm volatile("{\n.reg .pred p, q;\nsetp.eq.s32 p, %7, 0;\nsetp.eq.s32 q, %7, 31;\n@p ld.shared.v4.u32 {%0,%1,%2,%3}, [%6];\n@q ld.shared.v2.u32 {%4,%5}, [%6];\n}"
                                 : "+r"(lo[c][0]), "+r"(lo[c][1]), "+r"(lo[c][2]), "+r"(lo[c][3]), "+r"(hi[c][0]), "+r"(hi[c][1]) : "r"(ea + c * ULEN * 2), "r"(lane) : "memory");
#pragma unroll
                for (int c = c0; c < c1; c++) {
                    const uint32_t e[9] = {lo[c][1], lo[c][2], lo[c][3], uw[c][0], uw[c][1], uw[c][2], uw[c][3], hi[c][0], hi[c][1]};
                    uint32_t o[8], p[8], t[7], b3[5], b5[7];
#pragma unroll
                    for (int i = 0; i < 8; i++) { o[i] = __byte_perm(e[i], e[i + 1], 0x5432); p[i] = add2(e[i], o[i]); }
#pragma unroll
                    for (int i = 0; i < 5; i++) b3[i] = add2(o[i], p[i + 1]);
                    sts4(bx + c * BX_LEN + BX_3 + 160, b3);
#pragma unroll
                    for (int i = 1; i < 7; i++) { t[i] = add2(p[i], p[i + 1]); b5[i] = add2(t[i], e[i + 2]); }
                    sts4(bx + c * BX_LEN + BX_5 + 160, b5 + 2);
                    if (full) {
#pragma unroll
                        for (int i = 1; i < 5; i++) { b3[i] = add2(b3[i], t[i + 2]); t[i] = add2(t[i], b5[i + 2]); }
                        sts4(bx + c * BX_LEN + BX_7 + 272, b3 + 1);
                        sts4(bx + c * BX_LEN + BX_9 + 272, t + 1);
                    }
                }
            };
            auto reload = [&](int c, uint32_t a) { const uint4 v = lds4(a); uw[c][0] = v.x; uw[c][1] = v.y; uw[c][2] = v.z; uw[c][3] = v.w; };
            if (warp >= 6) {
#pragma unroll
                for (int c = 0; c < 3; c++) reload(c, ua - 1024 + (c + 2) * ULEN * 2);
            }
            if (warp >= 4) {
#pragma unroll
                for (int c = 3; c < 5; c++) reload(c, ua - 2048 + c * ULEN * 2);
            }
            box(Int<0>(), Int<3>(), warp < 6 ? tid : tid - 64, warp < 6 ? 0 : 2, warp < 4);
            if (warp >= 4) box(Int<3>(), Int<5>(), tid - 128, 0, true);
            else if (tid >= 128 - CV_CPB) {
                const int c = 127 - tid;
                const uint2 v = *reinterpret_cast<const uint2*>(Us + c * ULEN + UPADF);
                const float s1 = __uint_as_float(v.x << 16), s2 = s1 + __uint_as_float(v.x & 0xffff0000u), s3 = s2 + __uint_as_float(v.y << 16), s4 = s3 + __uint_as_float(v.y & 0xffff0000u);
                unsigned char* bc = sm + CV_SM_B + c * BX_LEN;
                *reinterpret_cast<uint32_t*>(bc + BX_5 + 156) = pack2(s1, s2);
                *reinterpret_cast<uint2*>(bc + BX_7 + 264) = make_uint2(v.x << 16, pack2(s2, s3));
                *reinterpret_cast<uint2*>(bc + BX_9 + 264) = make_uint2(pack2(s1, s2), pack2(s3, s4));
            }
        }
        __syncwarp();
        if (lane == 0) mbar_arrive(cnt + 40);
        TSTAMP(2); CST(2);
        if (layer && blockIdx.x == 0 && tid == 224) g_epoch = ld_epoch();
        __syncwarp();
        if ((0x6e >> warp) & 1) {
            constexpr int seq[16] = {0, 1, 2, 3, 4, 5, 6, 32, 7, 8, 9, 33, 10, 34, 11, 12};
            uint2 f[20];
            mbar_wait(cnt, 0);
            const uint32_t e8 = lc.e4 + 428 - (lane & 28);
#pragma unroll
            for (int k = 0; k < 13; k++) f[k] = make_uint2(lds1(k < 10 ? lc.e4 + 32 * k + 16 : e8 + 32 * k - 304), lds1(k < 10 ? lc.e4 + 32 * k : e8 + 32 * k - 320));
            f[19] = make_uint2(lds1(lc.en), lds1(lc.en - 32));
            far(Int<4>(), seq, lc, tc, lane, f, lds1(smem_u32(sm + CV_SM_T) + TAPB * tc + TAPE + 1672));
        }
    }
    {
        CV_IDX
        if ((0xc91 >> warp) & 1) {
            const int c = __popc(0xc91 & ((1 << warp) - 1));
            uint4 xv[2], yv[2];
#pragma unroll
            for (int k = 0; k < 2; k++) xv[k] = ldx(smem_u32(Xs + c * XLEN) + 512 * k + (lane >> 4) * 256 + (lane & 15) * 8);
            const uint32_t u0 = lds1(smem_u32(Us + c * ULEN) + (lane == 31 ? UPADF * 2 : 0));
            mbar_wait(cnt + 8 * c, 0);
#pragma unroll
            for (int k = 0; k < 2; k++) yv[k] = lds4(smem_u32(sm + CV_SM_Y) + c * 8192 + 512 * k + usw(lane) * 16);
            const uint4 yz = lds4(smem_u32(sm + CV_SM_Y) + c * 8192 + 4096 + usw(lane) * 16);
            const float kk = __uint_as_float(lds1(smem_u32(sm + CV_SM_T) + TAPB * c + TAPE + 1272) << 16);
            yv[1].x = add2(yv[1].x, yz.x); yv[1].y = add2(yv[1].y, yz.y); yv[1].z = add2(yv[1].z, yz.z);
            yv[1].w = pack2(fmaf(kk, __uint_as_float(u0 << 16), __uint_as_float(yv[1].w << 16) + __uint_as_float(yz.w << 16)),
                            fmaf(kk, __uint_as_float(u0 << 16) + __uint_as_float(u0 & 0xffff0000u), __uint_as_float(yv[1].w & 0xffff0000u) + __uint_as_float(yz.w & 0xffff0000u)));
#pragma unroll
            for (int k = 0; k < 2; k++) cv_store(dq + c * XCP * 2 + (lane >> 4) * 256 + (lane & 15) * 8 + 512 * k, xv[k], yv[k]);
        }
        TSTAMP(4); CST(8);
        if (layer == 1) {
            const int rb = (blockIdx.x >> 3) + (warp & 8) * 2, cg = blockIdx.x & 7, ch = (tid >> 3) & 31;
            const bf16* src = dst + (size_t)(cg * 80 + ch) * XCP + rb * 64 + (tid & 7) * 8;
            uint32_t v[3][4];
            __syncthreads();
            if (warp & 8) { const uint32_t c0 = clock(); while (clock() - c0 < 300) ; }
            uint32_t todo = (warp & 4) ? 3 : 7;
#pragma unroll 1
            for (int it = 0; it < SPIN_MAX; it++) {
#pragma unroll
                for (int k = 0; k < 3; k++)
                    if (todo >> k & 1)
                        asm volatile("ld.relaxed.gpu.global.v4.u32 {%0,%1,%2,%3}, [%4];" : "=r"(v[k][0]), "=r"(v[k][1]), "=r"(v[k][2]), "=r"(v[k][3]) : "l"(src + k * (32 * XCP)) : "memory");
#pragma unroll
                for (int k = 0; k < 3; k++)
                    if ((todo >> k & 1) && v[k][0] != ~0u && v[k][1] != ~0u && v[k][2] != ~0u && v[k][3] != ~0u) {
                        *reinterpret_cast<uint4*>(sm + (32 * k + ch) * 272 + ((tid & 7) + (warp & 8)) * 16) = make_uint4(v[k][0], v[k][1], v[k][2], v[k][3]);
                        todo ^= 1u << k;
                    }
                if (!todo) break;
                __nanosleep(CV_SLEEP);
            }
            __syncwarp();
            asm volatile("bar.sync %0, 256;" ::"r"(8 + (warp >> 3)) : "memory");
            uint32_t w[12];
#pragma unroll
            for (int k = 0; k < 3; k++) ldsm_x4(&w[4 * k], smem_u32(sm) + min(32 * k + lane, 79) * 272 + warp * 16);
            const uint32_t ot = smem_u32(sm + CV_SM_O) + warp * 1280, oa = ot + (lane & 7) * 160 + (lane >> 3) * 16;
            stsm_x4_t(oa, w[0], w[1], w[2], w[3]);
            stsm_x4_t(oa + 64, w[4], w[5], w[6], w[7]);
            asm volatile("stmatrix.sync.aligned.m8n8.x2.trans.shared.b16 [%0], {%1,%2};" ::"r"(oa + 128), "r"(w[8]), "r"(w[9]) : "memory");
            fence_async_smem();
            __syncwarp();
            if (lane == 0) {
                asm volatile("cp.async.bulk.tensor.3d.global.shared::cta.bulk_group [%0, {%1, %2, %3}], [%4];" ::"l"(&tmOut), "r"(cg * 80), "r"((rb >> 1) * 64 + 8 * (warp & 7)), "r"(rb & 1), "r"(ot) : "memory");
                asm volatile("cp.async.bulk.commit_group;" ::: "memory");
                asm volatile("cp.async.bulk.wait_group.read 0;" ::: "memory");
            }
        }
    }
    TSTAMP(3); CST(9); CST_END;
    GSTAMP(g_tim, 14);
    SPAN(3 + 4 * layer, 3);
}

template <int TA, int TB>
__device__ __forceinline__ void wgmma_n240(float (&d)[120], uint64_t da, uint64_t db, int acc) {
    asm volatile("{\n.reg .pred p;\nsetp.ne.b32 p, %124, 0;\nwgmma.mma_async.sync.aligned.m64n240k16.f32.bf16.bf16 {%0,%1,%2,%3,%4,%5,%6,%7,%8,%9,%10,%11,%12,%13,%14,%15,%16,%17,%18,%19,%20,%21,%22,%23,%24,%25,%26,%27,%28,%29,%30,%31,%32,%33,%34,%35,%36,%37,%38,%39,%40,%41,%42,%43,%44,%45,%46,%47,%48,%49,%50,%51,%52,%53,%54,%55,%56,%57,%58,%59,%60,%61,%62,%63,%64,%65,%66,%67,%68,%69,%70,%71,%72,%73,%74,%75,%76,%77,%78,%79,%80,%81,%82,%83,%84,%85,%86,%87,%88,%89,%90,%91,%92,%93,%94,%95,%96,%97,%98,%99,%100,%101,%102,%103,%104,%105,%106,%107,%108,%109,%110,%111,%112,%113,%114,%115,%116,%117,%118,%119}, %120, %121, p, 1, 1, %122, %123;\n}"
                 : "+f"(d[0]), "+f"(d[1]), "+f"(d[2]), "+f"(d[3]), "+f"(d[4]), "+f"(d[5]), "+f"(d[6]), "+f"(d[7]), "+f"(d[8]), "+f"(d[9]), "+f"(d[10]), "+f"(d[11]), "+f"(d[12]), "+f"(d[13]), "+f"(d[14]), "+f"(d[15]), "+f"(d[16]), "+f"(d[17]), "+f"(d[18]), "+f"(d[19]), "+f"(d[20]), "+f"(d[21]), "+f"(d[22]), "+f"(d[23]), "+f"(d[24]), "+f"(d[25]), "+f"(d[26]), "+f"(d[27]), "+f"(d[28]), "+f"(d[29]), "+f"(d[30]), "+f"(d[31]), "+f"(d[32]), "+f"(d[33]), "+f"(d[34]), "+f"(d[35]), "+f"(d[36]), "+f"(d[37]), "+f"(d[38]), "+f"(d[39]), "+f"(d[40]), "+f"(d[41]), "+f"(d[42]), "+f"(d[43]), "+f"(d[44]), "+f"(d[45]), "+f"(d[46]), "+f"(d[47]), "+f"(d[48]), "+f"(d[49]), "+f"(d[50]), "+f"(d[51]), "+f"(d[52]), "+f"(d[53]), "+f"(d[54]), "+f"(d[55]), "+f"(d[56]), "+f"(d[57]), "+f"(d[58]), "+f"(d[59]), "+f"(d[60]), "+f"(d[61]), "+f"(d[62]), "+f"(d[63]), "+f"(d[64]), "+f"(d[65]), "+f"(d[66]), "+f"(d[67]), "+f"(d[68]), "+f"(d[69]), "+f"(d[70]), "+f"(d[71]), "+f"(d[72]), "+f"(d[73]), "+f"(d[74]), "+f"(d[75]), "+f"(d[76]), "+f"(d[77]), "+f"(d[78]), "+f"(d[79]), "+f"(d[80]), "+f"(d[81]), "+f"(d[82]), "+f"(d[83]), "+f"(d[84]), "+f"(d[85]), "+f"(d[86]), "+f"(d[87]), "+f"(d[88]), "+f"(d[89]), "+f"(d[90]), "+f"(d[91]), "+f"(d[92]), "+f"(d[93]), "+f"(d[94]), "+f"(d[95]), "+f"(d[96]), "+f"(d[97]), "+f"(d[98]), "+f"(d[99]), "+f"(d[100]), "+f"(d[101]), "+f"(d[102]), "+f"(d[103]), "+f"(d[104]), "+f"(d[105]), "+f"(d[106]), "+f"(d[107]), "+f"(d[108]), "+f"(d[109]), "+f"(d[110]), "+f"(d[111]), "+f"(d[112]), "+f"(d[113]), "+f"(d[114]), "+f"(d[115]), "+f"(d[116]), "+f"(d[117]), "+f"(d[118]), "+f"(d[119])
                 : "l"(da), "l"(db), "n"(TA), "n"(TB), "r"(acc));
}

__device__ __forceinline__ void wgmma_n80(float (&d)[40], uint64_t da, uint64_t db, int acc) {
    asm volatile("{\n.reg .pred p;\nsetp.ne.b32 p, %42, 0;\nwgmma.mma_async.sync.aligned.m64n80k16.f32.bf16.bf16 {%0,%1,%2,%3,%4,%5,%6,%7,%8,%9,%10,%11,%12,%13,%14,%15,%16,%17,%18,%19,%20,%21,%22,%23,%24,%25,%26,%27,%28,%29,%30,%31,%32,%33,%34,%35,%36,%37,%38,%39}, %40, %41, p, 1, 1, 0, 1;\n}"
                 : "+f"(d[0]), "+f"(d[1]), "+f"(d[2]), "+f"(d[3]), "+f"(d[4]), "+f"(d[5]), "+f"(d[6]), "+f"(d[7]), "+f"(d[8]), "+f"(d[9]), "+f"(d[10]), "+f"(d[11]), "+f"(d[12]), "+f"(d[13]), "+f"(d[14]), "+f"(d[15]), "+f"(d[16]), "+f"(d[17]), "+f"(d[18]), "+f"(d[19]), "+f"(d[20]), "+f"(d[21]), "+f"(d[22]), "+f"(d[23]), "+f"(d[24]), "+f"(d[25]), "+f"(d[26]), "+f"(d[27]), "+f"(d[28]), "+f"(d[29]), "+f"(d[30]), "+f"(d[31]), "+f"(d[32]), "+f"(d[33]), "+f"(d[34]), "+f"(d[35]), "+f"(d[36]), "+f"(d[37]), "+f"(d[38]), "+f"(d[39])
                 : "l"(da), "l"(db), "r"(acc));
}

constexpr int A1_THREADS = 384;
constexpr int A1_NST = 4;
#define A1_SKEW 8
constexpr int A1_STAGE = 16384 + WQ_STAGE;
constexpr int A1_KVP = 336;
constexpr int A1_SM_KV = 2 * A1_STAGE;
constexpr int A1_SM_END = A1_NST * A1_STAGE;
constexpr int A1_SM_BAR = A1_SM_END + 3072 + 3 * WOB + 64;
constexpr int A1_SM_RS = A1_SM_END + 512;
constexpr int A1_SM_W0 = A1_SM_END + 3072, A1_SM_W3 = A1_SM_END - 3 * WOB, A1_SM_A1 = 2 * WOB, A1_SM_A0 = A1_SM_A1 + 61440;
constexpr int A1_SM_XA = A1_SM_W0 + 2 * WOB, A1_SM_XB = A1_SM_XA + 2048;
constexpr int A1_SMEM = A1_SM_BAR + 512 + 7 * CST_EXTRA / 4;
static_assert(A1_SM_W3 >= A1_SM_KV + 144 * A1_KVP && A1_SM_W3 % 512 == 0 && A1_SM_A1 % 1024 == 0 && A1_SM_A0 <= A1_SM_KV && A1_SM_A0 + 61440 <= A1_SM_W3 && A1_SMEM <= 232448 && 11 * 4096 <= A1_STAGE, "layout");
__device__ __forceinline__ constexpr uint32_t wo_off(int h) { return h * WOB + (h < 3 ? A1_SM_W0 : h < 6 ? A1_SM_W3 - 3 * WOB : -6 * WOB); }
#define A1_FRED "red.relaxed.gpu.global.add.u32"
#define A1_FLD "ld.relaxed.gpu.global.u32"
#define ST_SLEEP 20
#define ST_SLEEP0 300
#define A1_P0 2
#define A1_PW (kb - 2)
#define A1_FSPIN SPIN_MAX
#define A1_FSLEEP 40
#define YT_LAYER 1
#define WOT 11
#define A1_WOAT 6

template <int L>
__device__ __forceinline__ void a1_mainloop(float (&acc)[120], uint32_t sbase, uint32_t bars, int wg, int tile) {
    constexpr int layer = L; (void)layer;
    const uint64_t da0 = L ? make_desc(sbase + wg * 8192, 8192, 1024, 1) : make_desc(sbase + wg * 8192, 16, 1024, 1), db0 = make_desc(sbase + 16384, 1024, 256, 3);
#pragma unroll 1
    for (int t = 0;; t++) {
        const int st = t % A1_NST;
        mbar_wait(bars + 8 * st, (t / A1_NST) & 1);
        if (t == A1_SKEW && wg == 0) mbar_wait(bars + 160, 0);
        TSTAMP3(1 + t);
        if (t == 0) CSA(0);
        wgmma_fence();
#pragma unroll
        for (int kk = 0; kk < 4; kk++) wgmma_n240<L, 1>(acc, da0 + (uint32_t)(st * (A1_STAGE / 16) + kk * (L ? 128 : 2)), db0 + (uint32_t)(st * (A1_STAGE / 16) + (kk >> 1) * (WQ_STAGE / 32) + (kk & 1) * 32), kk ? 1 : t);
        wgmma_commit();
        if (t == 9) break;
        if (t == A1_SKEW - 1 && wg == 0) wgmma_wait<0>(); else wgmma_wait<1>();
        if (t > 0 && (threadIdx.x & 127) == 0) {
            if (t != A1_SKEW || wg) mbar_arrive(bars + 8 * (A1_NST + (t - 1) % A1_NST));
            if (t == A1_SKEW - 1 && wg == 0) mbar_arrive(bars + 8 * (A1_NST + t % A1_NST));
        }
    }
}

template <bool MAP>
__global__ void __launch_bounds__(A1_THREADS, 1) a1_kernel(const __grid_constant__ Par in, const __grid_constant__ CUtensorMap tmX, const __grid_constant__ CUtensorMap tmR,
                                                           const __grid_constant__ CUtensorMap tmX1, const __grid_constant__ KgMaps tmW, const __grid_constant__ TileTab tab) {
#define layer in.layer
    const unsigned char* const wo = reinterpret_cast<const unsigned char*>(in.wop);
    float2* const rsum = reinterpret_cast<float2*>(in.sum);
    uint4* const of = in.of;
    extern __shared__ __align__(1024) unsigned char stg[];
    const uint32_t sbase = smem_u32(stg);
    const uint32_t bars = sbase + A1_SM_BAR;
    const uint32_t bar_stat = bars + 64, bar_kv = bars + 72, bar_rd = bars + 168;
    const uint32_t bar_wo = bars + 208, bar_done = bars + 216, bar_pv = bars + 224, bar_kvf = bars + 232, bar_f2 = bars + 248, bar_e2 = bars + 384, que = bars + 448;
    const int tid = threadIdx.x;
    CSK(0);
    const int w = __shfl_sync(~0u, tid >> 5, 0), wg = w >> 2;
    uint32_t smid;
    asm volatile("mov.u32 %0, %smid;" : "=r"(smid));
    const uint4 tv = tab.e[(MAP ? smid : blockIdx.x) + (tid & (smid >> 12))];
    const uint64_t pa = reinterpret_cast<const uint64_t*>(&in)[tid & (smid >> 12)], pb = reinterpret_cast<const uint64_t*>(&in)[6 + (tid & (smid >> 12))];
    const bool one = elect();
    uint32_t tz;
    const unsigned char* wq;
    auto entry = [&] { tz = __shfl_sync(~0u, tv.z, 0); wq = (const unsigned char*)(((uint64_t)__shfl_sync(~0u, tv.y, 0) << 32) | __shfl_sync(~0u, tv.x, 0)); };
    auto issue_w = [&](unsigned it) { bulk_load(sbase + (it % A1_NST) * A1_STAGE + 16384, wq + it * WQ_STAGE, WQ_STAGE, bars + 8 * (it % A1_NST)); };
    auto issue_x = [&](unsigned it, int kb) {
        asm volatile("cp.async.bulk.tensor.5d.shared::cluster.global.mbarrier::complete_tx::bytes [%0], [%1, {%3, %3, %3, %4, %5}], [%2];"
                     ::"r"(sbase + (it % A1_NST) * A1_STAGE), "l"(&tmX), "r"(bars + 8 * (it % A1_NST)), "r"(0), "r"(tz & 15), "r"(kb) : "memory");
    };
    auto first_x = [&] {
        issue_x(0, (tz >> 16) & 7); issue_x(1, ((tz >> 16) & 7) + 1);
    };
    auto expect = [&] {
#pragma unroll
        for (int i = 0; i < A1_NST; i++) mbar_expect_tx(bars + 8 * i, A1_STAGE);
    };
    if (w == 8) {
        if (one) {
            prefetch_tmap(&tmX); prefetch_tmap(&tmW.q);
#pragma unroll
            for (int i = 0; i < A1_NST; i++) mbar_init(bars + 8 * i, 1);
            asm volatile("fence.mbarrier_init.release.cluster;" ::: "memory");
        }
        __syncwarp();
        asm volatile("bar.arrive 0, 384;" ::: "memory");
        if (smid >> 12) __trap();
        entry();
        if ((tz & 0x80000010u) == 16) {
            if (one) {
                issue_w(0);
                asm volatile("griddepcontrol.wait;" ::: "memory");
                first_x();
                issue_w(1);
                expect();
                asm volatile("griddepcontrol.launch_dependents;" ::: "memory");
            }
#pragma unroll
            for (int kb = 2; kb < A1_NST; kb++) {
                __syncwarp();
                mbar_wait(bars + 8 * (kb - 2), 0);
                if (one) { issue_x(kb, ((tz >> 16) & 7) + kb); issue_w(kb); }
                CSK(6 + kb);
            }
        }
        __syncwarp();
        if (!(tz & 16) && blockIdx.x < 128) kgen_first(in, tmW, sbase + A1_SM_W0, bars - 24, one);
        __syncwarp();
    }
    if (w > 8) CSK(8);
    const bool gen = w != 8 && in.logA && blockIdx.x < 128;
    KgPar kp;
    const int w11 = w < 8 ? 2 * (w & 3) + (w >> 2) : w - 1;
    if (gen) kgen_load(in, reinterpret_cast<const bf16*>(pa), w11, kp);
    if (w > 8) CSK(9);
    if (w == 8) {
        const int tile = tz >> 24, mb = tz & 15, hg = (tz >> 8) & 7, kb0 = (tz >> 16) & 7;
        const unsigned l1 = (tz >> 4) & 1;
        if (__builtin_expect(!l1, 0)) {
            CSK(1);
            const uint32_t ep = ld_epoch();
            if (one) {
                kgen_side(in, sbase + A1_SM_W0, bars - 24);
                if (tile < 128) { first_x(); expect(); }
                asm volatile("cp.async.bulk.wait_group 0;" ::: "memory");
            }
            __syncwarp();
            asm volatile("bar.arrive 10, 96;" ::: "memory");
            CSK(6);
            if (tile < 128) {
                await_all(96 + 32 * hg, ep * 15);
                if (one) issue_w(0);
                __syncwarp();
                mbar_wait(bars, 0);
                if (one) { issue_w(1); issue_x(2, kb0 + 2); issue_w(2); }
            }
            CSK(7);
            asm volatile("bar.sync 3, 384;" ::: "memory");
            if (tile < 128 && one) {
                fence_async_smem();
                issue_x(3, kb0 + 3); issue_w(3);
                mbar_expect_tx(bars + 240, 20480);
                bulk_load(sbase + A1_SM_W0, in.x + (size_t)(mb * 128 + hg * 16) * DM, 20480, bars + 240);
            }
            __syncwarp();
            CSK(9);
        } else asm volatile("bar.sync 3, 64;" ::: "memory");
        if (tile < 128 && elect()) {
#pragma unroll 1
            for (unsigned kb = A1_NST; kb < 10; kb++) {
                mbar_wait(bars + 8 * (A1_NST + kb % A1_NST), ((kb / A1_NST) - 1) & 1);
                if (l1 && kb < 9) mbar_wait(bar_rd + 8 * (kb - A1_NST), 0);
                mbar_expect_tx(bars + 8 * (kb % A1_NST), A1_STAGE);
                issue_x(kb, kb < 5 ? kb + kb0 : kb - kb0); issue_w(kb);
                if (kb == (l1 ? A1_WOAT : 9)) {
                    if (!l1) { mbar_wait(bar_stat, 0); asm volatile("fence.proxy.async.global;" ::: "memory"); }
                    mbar_expect_tx(bar_wo, 8 * WOB);
                    bulk_load(sbase + A1_SM_W0, wo + hg * 8 * WOB, 2 * WOB, bar_wo);
                }
            }
            mbar_wait(bars + 8 * (A1_NST + 3), 1);
            bulk_load(sbase + A1_SM_W3, wo + (hg * 8 + 3) * WOB, 3 * WOB, bar_wo);
        }
        CSA(4); CSA_END;
        return;
    }
    {
        if (w < 8 && one) {
#pragma unroll 1
            for (uint32_t c = (w & 4 ? w & 2 ? 0x1111112'01111111ull : 0x1111111'01111184ull : w & 2 ? 0x3122222'01111111ull : 0x1111132'02220000ull) >> (32 * (w & 1)), b = bars + 56 * w; c; c >>= 4, b += 8)
                if (c & 15) mbar_init(b, c & 15);
            asm volatile("fence.mbarrier_init.release.cluster;" ::: "memory");
        }
        __syncwarp();
        asm volatile("bar.sync 0, 384;" ::: "memory");
        if (layer) {
            if (w == 9) asm volatile("bar.arrive 3, 64;" ::: "memory");
        } else {
            if (gen) { SPAN(0, 0); SPAN(0, 1); kgen_tables(in, reinterpret_cast<uint4*>(stg + 3 * A1_STAGE), w11, kp); }
            else if (w != 11 && w11 > 1) asm volatile("bar.arrive 9, 352;" ::: "memory");
            __syncwarp();
            if (w11 < 2) {
                asm volatile("bar.sync 10, 96;" ::: "memory");
                kgen_sums(in, sbase + A1_SM_W0, w11);
                __syncwarp();
                asm volatile("bar.arrive 9, 352;" ::: "memory");
                CSK(1);
            }
            if (w == 9) asm volatile("bar.sync 3, 384;" ::: "memory"); else asm volatile("bar.arrive 3, 384;" ::: "memory");
        }
    }
    tz = __shfl_sync(~0u, tv.z + (uint32_t)(pb >> 32), 0);
    const int tile = tz >> 24, mb = tz & 15, hg = (tz >> 8) & 7;
    float2* rst = reinterpret_cast<float2*>(stg + A1_SM_RS) + 8;
    if (wg == 2) {
        if (w == 11 && layer == 0) {
            asm volatile("bar.sync 9, 352;" ::: "memory");
            CSK(5);
            if (one) publish(64);
            __syncwarp();
            CSK(6);
        }
        if (tile >= 128) { sm_idle(layer); return; }
        if (w == 10) {
            if (one) { prefetch_tmap(&tmR); prefetch_tmap(&tmX1); }
            uint32_t ns;
            asm volatile("mov.u32 %0, %nsmid;" : "=r"(ns));
            if (MAP && ns != 132) __trap();
        }
        __syncwarp();
        if (w == 9) {
            if (layer && one) {
                mbar_expect_tx(bar_stat, 3840);
                bulk_load(sbase + A1_SM_XB, g_xb + tile * 240, 3840, bar_stat);
            }
            __syncwarp();
            uint4* pre = of + (mb * 8 + hg) * 1280 + (tid - 288);
#pragma unroll 1
            for (int k = 0; k < 5 + 5 * layer; k++) {
#pragma unroll
                for (int i = 0; i < 8; i++) asm volatile("st.global.v4.u32 [%0], {%1,%1,%1,%1};" ::"l"(pre + 32 * i), "r"(~0u) : "memory");
                pre += k < 5 ? 256 : XCP / 8;
                if (k == 4) {
                    CSA(2);
                    asm volatile("fence.acq_rel.gpu;" ::: "memory");
                    asm volatile("fence.proxy.async.global;" ::: "memory");
                    __syncwarp();
                    if (tid == 288) mbar_arrive(bar_done);
                    CSA(3);
                    pre = reinterpret_cast<uint4*>(g_yT) + tile * (5 * XCP / 8) + (tid - 288);
                }
            }
            if (layer == 0) {
                asm volatile("griddepcontrol.launch_dependents;" ::: "memory");
                await_all(64, ld_epoch() * gridDim.x);
                CSA(5);
                float4 a[2] = {};
#pragma unroll
                for (int k = 0; k < 10; k++)
#pragma unroll
                    for (int h = 0; h < 2; h++) {
                        const int c4 = min(tid - 288 + 32 * h, 59);
                        const float4 v = __ldcg(reinterpret_cast<const float4*>(g_csp + (k / 5) * 9600 + (k % 5) * 640 + hg * 80) + c4 + (c4 / 20) * 780);
                        a[h].x += v.x; a[h].y += v.y; a[h].z += v.z; a[h].w += v.w;
                    }
#pragma unroll
                for (int h = 0; h < 2; h++)
#pragma unroll
                    for (int k = 0; k < 4; k++) {
                        const float c = 0.5f * (k == 0 ? a[h].x : k == 1 ? a[h].y : k == 2 ? a[h].z : a[h].w), c1 = c - rbf(c), c2 = c1 - rbf(c1);
                        *reinterpret_cast<uint4*>(stg + A1_SM_XB + (4 * min(tid - 288 + 32 * h, 59) + k) * 16) = make_uint4(pack2(c, c1), pack2(c2, 0.f), 0u, 0u);
                    }
                fence_async_smem();
                __syncwarp();
                if (one) {
                    bulk_store(g_xb + tile * 240, sbase + A1_SM_XB, 3840);
                    asm volatile("cp.async.bulk.commit_group;" ::: "memory");
                    asm volatile("cp.async.bulk.wait_group.read 0;" ::: "memory");
                    mbar_arrive(bar_stat);
                }
                __syncwarp();
                CSA(1);
            }
            TSTAMP1T(9, 288);
        } else {
            const int j = tid - 320;
            const uint32_t tag = ld_epoch();
            if (tid == 352) sm_started(layer);
            const int ch = j & 7, kg = (j >> 3) & 3;
            const unsigned char* src = stg + (layer ? (j >> 5) * 8192 + (hg & 3) * 2048 : A1_SM_W0 + (j >> 2) * 1280);
            const int of0 = layer ? kg * 128 + ((ch ^ kg) << 4) : (j & 7) << 4, ofx = layer ? 576 : 64, ofy = layer ? 1024 : 128;
            float s[8], q[8], p0[8];
#pragma unroll
            for (int i = 0; i < 8; i++) { s[i] = 0.f; q[i] = 0.f; }
#pragma unroll 1
            for (int it = 0; it < 5; it++) {
                uint4 v[4];
                mbar_wait(layer ? bars + 8 * (it % A1_NST) : bars + 240, layer * it / A1_NST);
#pragma unroll
                for (int k = 0; k < 4; k++) v[k] = *reinterpret_cast<const uint4*>(src + (layer ? (it % A1_NST) * A1_STAGE : it * 256) + (k & 1 ? of0 ^ ofx : of0) + (k >> 1) * ofy);
                if (it == 0) {
                    const uint4 pv = *reinterpret_cast<const uint4*>(src + (layer ? ch << 4 : 0));
                    const uint32_t w[4] = {pv.x, pv.y, pv.z, pv.w};
#pragma unroll
                    for (int i = 0; i < 4; i++) { p0[2 * i] = __uint_as_float((layer ? w[i] : w[0]) << 16); p0[2 * i + 1] = __uint_as_float(layer ? w[i] & 0xffff0000u : w[0] << 16); }
                }
                asm volatile("" :: "r"(v[0].x), "r"(v[1].x), "r"(v[2].x), "r"(v[3].x), "f"(p0[0]) : "memory");
                __syncwarp();
                if ((tid & 31) == 0) mbar_arrive(bar_rd + 8 * it);
#pragma unroll
                for (int k = 0; k < 4; k++) {
                    const uint32_t w[4] = {v[k].x, v[k].y, v[k].z, v[k].w};
#pragma unroll
                    for (int i = 0; i < 4; i++) {
                        const float a = __uint_as_float(w[i] << 16) - p0[2 * i], b = __uint_as_float(w[i] & 0xffff0000u) - p0[2 * i + 1];
                        s[2 * i] += a; s[2 * i + 1] += b; q[2 * i] = fmaf(a, a, q[2 * i]); q[2 * i + 1] = fmaf(b, b, q[2 * i + 1]);
                    }
                }
            }
            float o[4];
            int row;
            if (layer == 0) {
                float s0 = ((s[0] + s[1]) + (s[2] + s[3])) + ((s[4] + s[5]) + (s[6] + s[7])), q0 = ((q[0] + q[1]) + (q[2] + q[3])) + ((q[4] + q[5]) + (q[6] + q[7]));
#pragma unroll
                for (int o = 1; o <= 2; o <<= 1) { s0 += __shfl_xor_sync(~0u, s0, o); q0 += __shfl_xor_sync(~0u, q0, o); }
                if ((j & 3) == 0) {
                    const float d = s0 * (1.0f / DM);
                    const uint32_t ms = pack2(p0[0] + d, sqrt_apx(rbf(rbf(fmaxf(fmaf(-d, d, q0 * (1.0f / DM)), 0.f)) + 1e-5f)));
                    asm volatile("st.global.cg.u64 [%0], %1;" ::"l"(g_rstat + mb * 128 + (j & 4) * 16 + hg * 8 + (j >> 3)), "l"(tagw(ms, tag)) : "memory");
                    g_piv[mb * 128 + hg * 16 + ((j >> 2) & 8) + (j & 4) + ((j >> 3) & 3)] = __ushort_as_bfloat16((unsigned short)ms);
                }
                ulonglong2 v;
#pragma unroll 1
                for (int it = 0; it < SPIN_MAX; it++) {
                    v = ld_tag2(reinterpret_cast<const ulonglong2*>(g_rstat + mb * 128) + j);
                    if (__all_sync(~0u, tag_ok(v, tag))) break;
                    __nanosleep(100);
                }
                o[0] = __uint_as_float((uint32_t)v.x << 16); o[1] = rcp_apx(__uint_as_float((uint32_t)v.x & 0xffff0000u));
                o[2] = __uint_as_float((uint32_t)v.y << 16); o[3] = rcp_apx(__uint_as_float((uint32_t)v.y & 0xffff0000u));
                row = 2 * j;
            } else {
#pragma unroll
                for (int i = 0; i < 4; i++) {
                    const bool up = kg & 2;
                    const float ss = __shfl_xor_sync(~0u, up ? s[i] : s[i + 4], 16), qq = __shfl_xor_sync(~0u, up ? q[i] : q[i + 4], 16);
                    s[i] = (up ? s[i + 4] : s[i]) + ss; q[i] = (up ? q[i + 4] : q[i]) + qq; p0[i] = up ? p0[i + 4] : p0[i];
                }
#pragma unroll
                for (int i = 0; i < 2; i++) {
                    const bool up = kg & 1;
                    const float ss = __shfl_xor_sync(~0u, up ? s[i] : s[i + 2], 8), qq = __shfl_xor_sync(~0u, up ? q[i] : q[i + 2], 8);
                    s[i] = (up ? s[i + 2] : s[i]) + ss; q[i] = (up ? q[i + 2] : q[i]) + qq; p0[i] = up ? p0[i + 2] : p0[i];
                }
                uint4* gp = g_halo + 86016 + mb * 512 + j;
                const float d0 = s[0] * (1.0f / 80.0f), d1 = s[1] * (1.0f / 80.0f);
                asm volatile("st.relaxed.gpu.global.v4.f32 [%0], {%1,%2,%3,%4};" ::"l"(gp + hg * 64), "f"(p0[0] + d0), "f"(fmaxf(fmaf(-d0, s[0], q[0]), 0.f)), "f"(p0[1] + d1), "f"(fmaxf(fmaf(-d1, s[1], q[1]), 0.f)) : "memory");
                __nanosleep(ST_SLEEP0);
                uint32_t pw[8][4], todo = 0xff;
#pragma unroll 1
                for (int it = 0; it < SPIN_MAX; it++) {
#pragma unroll
                    for (int k = 0; k < 8; k++)
                        if (todo >> k & 1) asm volatile("ld.relaxed.gpu.global.v4.u32 {%0,%1,%2,%3}, [%4];" : "=r"(pw[k][0]), "=r"(pw[k][1]), "=r"(pw[k][2]), "=r"(pw[k][3]) : "l"(gp + k * 64) : "memory");
#pragma unroll
                    for (int k = 0; k < 8; k++)
                        if (__all_sync(~0u, pw[k][0] != ~0u && pw[k][1] != ~0u && pw[k][2] != ~0u && pw[k][3] != ~0u)) todo &= ~(1u << k);
                    if (!todo) break;
                    __nanosleep(ST_SLEEP);
                }
#pragma unroll
                for (int r = 0; r < 2; r++) {
                    float mean = 0.f, m2 = 0.f;
#pragma unroll
                    for (int k = 0; k < 8; k++) mean += __uint_as_float(pw[k][2 * r]);
                    mean *= 0.125f;
#pragma unroll
                    for (int k = 0; k < 8; k++) {
                        const float dm = __uint_as_float(pw[k][2 * r]) - mean;
                        m2 += fmaf(80.0f * dm, dm, __uint_as_float(pw[k][2 * r + 1]));
                    }
                    o[2 * r] = rbf(mean);
                    o[2 * r + 1] = rcp_apx(rbf(sqrt_apx(rbf(rbf(m2 * (1.0f / DM)) + 1e-5f))));
                }
                row = (j >> 5) * 64 + (j & 7) * 8 + ((j >> 3) & 3) * 2;
                if (hg == 0) *reinterpret_cast<uint32_t*>(g_piv + SEQ + mb * 128 + 2 * (row & 60) + 4 * (row >> 6) + (row & 3)) = __byte_perm(__float_as_uint(o[0]), __float_as_uint(o[2]), 0x7632);
            }
#pragma unroll
            for (int r = 0; r < 2; r++)
                *reinterpret_cast<uint4*>(stg + A1_SM_XA + (row + r) * 16) = make_uint4(__byte_perm(__float_as_uint(-o[2 * r]), 0, 0x3232), __float_as_uint(-o[2 * r]) >> 16, 0u, 0u);
            *reinterpret_cast<float4*>(rst + row + (row >> 6) * 8) = make_float4(o[0], o[1], o[2], o[3]);
            fence_async_smem();
            TSTAMP1T(7, 320); CSA(1);
            if (tid == 320) DBGC(44);
            __syncwarp();
            if ((tid & 31) == 0) mbar_arrive(bar_stat);
        }
        CSA(4); CSA_END;
        if (tid == 320) DBGCAL(0);
        __syncwarp();
        if (w == WOT) {
            mbar_wait(bars + 416, 0);
            mbar_wait(bar_done, 0);
            if (one) {
                bulk_load(sbase, wo + (hg * 8 + 6) * WOB, 2 * WOB, bar_wo);
                bulk_load(sbase + A1_SM_W0 + 2 * WOB, wo + (hg * 8 + 2) * WOB, WOB, bar_wo);
            }
            __syncwarp();
        }
#define FWA 11
#define FWB 10
        if (w == FWA || w == FWB) {
            const int cw = w == FWB;
            const uint32_t* fl = reinterpret_cast<const uint32_t*>(rsum + 2 * SEQ) + (((layer * 16 + mb) * 2 + cw) * 8 + (tid & 7)) * FSTR;
            const unsigned char* src = reinterpret_cast<const unsigned char*>(of) + mb * 163840 + cw * 10240 + (tid & 7) * 20480;
            const uint32_t sl = sbase + (cw ? A1_SM_A1 : A1_SM_A0);
            mbar_wait(cw ? bar_done : bar_kvf, 0);
            if (one) {
                mbar_expect_tx(bar_f2 + 64 * cw + 64, 10240);
                tma_load_3d(sl + 51200, &tmR, layer ? 0 : hg * 80, layer ? hg * 80 : mb * 64, layer ? mb * 2 + cw : cw, bar_f2 + 64 * cw + 64);
            }
            __syncwarp();
            uint32_t pend = 0xffu & ~(1u << hg), v = 0;
            const uint32_t bo = wo_off((tid & 7) + ((tid & 7) < hg)) >> 4, lt = (1u << (tid & 31)) - 1;
#pragma unroll 1
            for (int it = 0; pend && it < 2 * SPIN_MAX; it++) {
                if (v != 4 && (pend >> (tid & 31) & 1)) asm volatile(A1_FLD " %0, [%1];" : "=r"(v) : "l"(fl) : "memory");
                uint32_t fr;
                asm volatile("{\n.reg .pred p;\nmbarrier.test_wait.parity.shared::cta.b64 p, [%1], 0;\nselp.b32 %0, 1, 0, p;\n}" : "=r"(fr) : "r"(bar_e2 + 16 * cw + (tid & 1) * 8) : "memory");
                fr = __ballot_sync(~0u, fr);
                uint32_t m = __ballot_sync(~0u, v == 4 || it >= A1_FSPIN) & pend;
                const int q = 8 - __popc(pend) + __popc(m & lt);
                m &= __ballot_sync(~0u, q < ((fr & 2) ? 8 : (fr & 1) ? 7 : 5));
                pend ^= m;
                if (m >> (tid & 31) & 1) DBGC(12 + cw * 8 + (tid & 7));
                if (!m) __nanosleep(A1_FSLEEP);
                if (m >> (tid & 31) & 1) {
                    bulk_load(q == 7 && !cw ? sbase + A1_SM_W0 : sl + (q < 6 ? q : q - 6) * 10240, src, 10240, bar_f2 + 64 * cw + 8 * q);
                    asm volatile("st.shared.u32 [%0], %1;" ::"r"(que + 32 * cw + 4 * q), "r"(bo) : "memory");
                    mbar_expect_tx(bar_f2 + 64 * cw + 8 * q, 10240);
                    DBGC(44 + cw * 8 + q);
                }
                __syncwarp();
            }
        }
    } else if (tile < 128) {
        SPAN(1 + 4 * layer, 0);
        constexpr int on = 1;
        float acc[120];
        const int lane = tid & 31, warp = w & 7, g = lane >> 2, t = lane & 3;
        if (on) {
            SPAN(1 + 4 * layer, 1);
            TSTAMP1(0);
            if (threadIdx.x == 0) { GSTAMP(g_tim1, 15); }
            TSTAMP3(0);
            if (tid == 0) TSTAMP2(0);
            TSTAMP4(0);
            if (tid == 0) DBGC(60);
            if (layer == 0) a1_mainloop<0>(acc, sbase, bars, wg, tile); else a1_mainloop<1>(acc, sbase, bars, wg, tile);
            uint32_t ok;
            asm volatile("{\n.reg .pred p;\nmbarrier.test_wait.parity.shared::cta.b64 p, [%1], 0;\nselp.b32 %0, 1, 0, p;\n}" : "=r"(ok) : "r"(bar_stat) : "memory");
            if (tid == 128 && !ok) mbar_arrive(bars + 160);
            __syncwarp();
            mbar_wait(bar_stat, 0);
            wgmma_fence();
            wgmma_n240<0, 0>(acc, make_desc(sbase + A1_SM_XA + wg * 1024, 0, 128, 0), make_desc(sbase + A1_SM_XB, 0, 128, 0), 1);
            wgmma_commit();
            if (tid == 128 && ok) mbar_arrive(bars + 160);
            mbar_wait(bars + 8 * (A1_NST + 3), 1);
        }
        uint4* hp = g_halo + (((layer * 16 + mb - ((warp & 3) != 3)) * 8 + hg) * 2 + wg) * 168 + lane;
        float* hr = reinterpret_cast<float*>(hp - lane + 160) + ((warp & 3) == 3 ? g : 2 * t);
        asm volatile("" : "+l"(hp), "+l"(hr));
        const float2* rw = rst + 16 * warp + 8 * wg;
        const float rb0 = rw[g + 8].y, ra = rw[g].y * 0.22360679774997896f, rb = rb0 * 0.22360679774997896f;
        wgmma_wait<0>();
        if ((tid & 127) == 0) mbar_arrive(bar_done);
        TSTAMP1(2); CSA(1);
        TSTAMP1T(13, 224);
        if ((tid & 127) == 0) DBGC(62 - wg);
        uint32_t f[2][30];
#pragma unroll
        for (int j = 10; j < 30; j++) f[1][j] = pack2(acc[4 * j + 2], acc[4 * j + 3]);
        if ((warp & 3) == 3) {
#pragma unroll
            for (int j = 0; j < 20; j += 4) {
                const int a = j < 12 ? 10 + j : 8 + j, b = j == 8 ? 28 : a + 2;
                asm volatile("st.relaxed.gpu.global.v4.u32 [%0], {%1,%2,%3,%4};" ::"l"(hp + 8 * j), "r"(f[1][a]), "r"(f[1][a + 1]), "r"(f[1][b]), "r"(f[1][b + 1]) : "memory");
            }
            if (t == 0) asm volatile("st.relaxed.gpu.global.f32 [%0], %1;" ::"l"(hr), "f"(rb0) : "memory");
        }
        TSTAMP1T(12, 224);
        const uint32_t kvw = sbase + A1_SM_KV + (16 * warp + 8 * wg) * A1_KVP;
        const uint32_t mrow = kvw + (lane & 7) * A1_KVP + (lane >> 3) * 16;
#pragma unroll
        for (int j = 0; j < 20; j += 4) {
            const int a = j < 12 ? 10 + j : 8 + j, b = j == 8 ? 28 : a + 2;
            stsm_x4(mrow + 16 * A1_KVP + 16 * (a - 10) + (j == 8 ? (lane & 16) * 8 : 0), f[1][a], f[1][a + 1], f[1][b], f[1][b + 1]);
        }
        __syncwarp();
        if (lane == 0 && (warp & 3) != 3) mbar_arrive(bar_kv + 8 * (warp + 1));
#pragma unroll
        for (int j = 0; j < 30; j++) f[0][j] = pack2(acc[4 * j], acc[4 * j + 1]);
        stsm_x4(mrow + 8 * A1_KVP + 160, f[0][20], f[0][21], f[0][22], f[0][23]);
        stsm_x4(mrow + 8 * A1_KVP + 224, f[0][24], f[0][25], f[0][26], f[0][27]);
        asm volatile("stmatrix.sync.aligned.m8n8.x2.shared.b16 [%0], {%1,%2};" ::"r"(mrow + 8 * A1_KVP + 288), "r"(f[0][28]), "r"(f[0][29]) : "memory");
#pragma unroll
        for (int j = 0; j < 10; j++) f[1][j] = pack2(acc[4 * j + 2], acc[4 * j + 3]);
        __syncwarp();
        uint32_t vb[10][2], hv[24] = {}, *kp = hv, *vp = hv + 12;
#pragma unroll
        for (int j = 0; j < 10; j += 2) ldsm_x4_t(&vb[j][0], kvw + (8 + (lane & 15)) * A1_KVP + 160 + (lane >> 4) * 16 + 16 * j);
        const bool up0 = 2 * t > g, up1 = 2 * t + 1 > g, edge = (mb | (warp & 3)) == 0;
        float rk[4];
        auto above = [&]() {
            mbar_wait(bar_kv + 8 * warp, 0);
#pragma unroll
            for (int j = 0; j < 12; j += 4) ldsm_x4(&kp[j], mrow + 16 * j);
            rk[0] = rw[2 * t - (up0 ? 8 : 0)].y; rk[1] = rw[2 * t + 1 - (up1 ? 8 : 0)].y;
#pragma unroll
            for (int j = 0; j < 8; j += 4) ldsm_x4_t(&vp[j], mrow + 160 + 16 * j);
            asm volatile("ldmatrix.sync.aligned.m8n8.x2.trans.shared.b16 {%0,%1}, [%2];" : "=r"(vp[8]), "=r"(vp[9]) : "r"(mrow + 288) : "memory");
            __syncwarp();
            if (lane == 0) mbar_arrive(bar_kvf);
        };
        auto ask = [&]() {
            if (mb > 0) {
#pragma unroll
                for (int k = 0; k < 20; k += 4)
                    asm volatile("ld.relaxed.gpu.global.v4.u32 {%0,%1,%2,%3}, [%4];" : "=r"(hv[k]), "=r"(hv[k + 1]), "=r"(hv[k + 2]), "=r"(hv[k + 3]) : "l"(hp + 8 * k) : "memory");
                asm volatile("ld.relaxed.gpu.global.v2.u32 {%0,%1}, [%2];" : "=r"(hv[20]), "=r"(hv[21]) : "l"(hr) : "memory");
            }
        };
        auto halo = [&]() {
            if (lane == 0) mbar_arrive(bar_kvf);
            rk[0] = rw[2 * t].y; rk[1] = rw[2 * t + 1].y;
#pragma unroll 1
            for (int it = 0; it < SPIN_MAX; it++) {
                uint32_t m = max(hv[20], hv[21]);
#pragma unroll
                for (int k = 0; k < 20; k += 2) m = __vimax3_u32(m, hv[k], hv[k + 1]);
                if (!__any_sync(~0u, m == ~0u)) break;
                ask();
            }
            if (wg && lane == 0) mbar_arrive(bars + 416);
            if (up0) rk[0] = __uint_as_float(hv[20]);
            if (up1) rk[1] = __uint_as_float(hv[21]);
#pragma unroll
            for (int j = 0; j < 10; j++) asm volatile("movmatrix.sync.aligned.m8n8.trans.b16 %0, %1;" : "=r"(vp[j]) : "r"(hv[j < 8 ? 12 + j : 2 + j]));
        };
        rk[2] = rw[2 * t + (up0 ? 0 : 8)].y; rk[3] = rw[2 * t + 1 + (up1 ? 0 : 8)].y;
        uint32_t qs[4][2];
#pragma unroll
        for (int h = 0; h < 4; h++) {
            qs[h][0] = (t >> 1) == (h & 1) ? f[0][5 * (h >> 1) + 2] : 0u; qs[h][1] = (t >> 1) == (h & 1) ? f[1][5 * (h >> 1) + 2] : 0u;
            asm volatile("" : "+r"(qs[h][0]), "+r"(qs[h][1]));
        }
#pragma unroll
        for (int j = 0; j < 10; j++) asm volatile("" : "+r"(f[0][j]), "+r"(f[1][j]), "+r"(f[0][10 + j]));
        if (warp & 3) above(); else if (wg) ask(); else hv[20] = mb ? ~0u : 0u;
        TSTAMP1T(10, 64); CSA(2);
        if (warp && !wg) mbar_wait(bars + 416 + 8 * warp, 0);
        CSA(3);
        float sc[4][3][4];
#pragma unroll
        for (int h = 0; h < 4; h++) {
            const int jb = 5 * (h >> 1) + 3 * (h & 1), js = 5 * (h >> 1) + 2;
#pragma unroll
            for (int nt = 1; nt < 3; nt++) {
#pragma unroll
                for (int e = 0; e < 4; e++) sc[h][nt][e] = 0.f;
                mma_bf16(sc[h][nt], f[0][jb], f[1][jb], f[0][jb + 1], f[1][jb + 1], f[nt - 1][10 + jb], f[nt - 1][11 + jb]);
                mma_bf16_k8(sc[h][nt], qs[h][0], qs[h][1], f[nt - 1][10 + js]);
            }
        }
        if (!(warp & 3)) halo();
        TSTAMP1(8); CSA(4);
#pragma unroll
        for (int h = 0; h < 4; h++) {
            const int jb = 5 * (h >> 1) + 3 * (h & 1), js = 5 * (h >> 1) + 2;
#pragma unroll
            for (int e = 0; e < 4; e++) sc[h][0][e] = 0.f;
            mma_bf16(sc[h][0], f[0][jb], f[1][jb], f[0][jb + 1], f[1][jb + 1], kp[jb], kp[jb + 1]);
            mma_bf16_k8(sc[h][0], qs[h][0], qs[h][1], kp[js]);
        }
        TSTAMP1T(3, 64);
        float p[4][4], sum[4][2];
        uint32_t lg[4][2], mx[4];
        const float rl[4] = {rk[0] * ra, rk[1] * ra, rk[2] * rb, rk[3] * rb};
        auto max2 = [](uint32_t a, uint32_t b) { uint32_t r; asm("max.bf16x2 %0, %1, %2;" : "=r"(r) : "r"(a), "r"(b)); return r; };
#pragma unroll
        for (int h = 0; h < 4; h++) {
            lg[h][0] = pack2((up0 ? sc[h][0][0] : sc[h][1][0]) * rl[0], (up0 ? sc[h][1][2] : sc[h][2][2]) * rl[2]);
            lg[h][1] = pack2((up1 ? sc[h][0][1] : sc[h][1][1]) * rl[1], (up1 ? sc[h][1][3] : sc[h][2][3]) * rl[3]);
            if (edge) {
                if (up0) lg[h][0] = __byte_perm(lg[h][0], 0xce6eu, 0x3254);
                if (up1) lg[h][1] = __byte_perm(lg[h][1], 0xce6eu, 0x3254);
            }
            mx[h] = max2(lg[h][0], lg[h][1]);
        }
#pragma unroll
        for (int o = 1; o <= 2; o <<= 1)
#pragma unroll
            for (int h = 0; h < 4; h++) mx[h] = max2(mx[h], __shfl_xor_sync(~0u, mx[h], o));
#pragma unroll
        for (int h = 0; h < 4; h++)
#pragma unroll
            for (int r = 0; r < 2; r++) {
                const float m = __uint_as_float(r ? mx[h] & 0xffff0000u : mx[h] << 16);
#pragma unroll
                for (int e = 0; e < 2; e++)
                    asm("ex2.approx.ftz.f32 %0, %1;" : "=f"(p[h][2 * r + e]) : "f"((__uint_as_float(r ? lg[h][e] & 0xffff0000u : lg[h][e] << 16) - m) * 1.4426950408889634f));
                sum[h][r] = p[h][2 * r] + p[h][2 * r + 1];
            }
#pragma unroll
        for (int o = 1; o <= 2; o <<= 1)
#pragma unroll
            for (int h = 0; h < 4; h++)
#pragma unroll
                for (int r = 0; r < 2; r++) sum[h][r] += __shfl_xor_sync(~0u, sum[h][r], o);
        TSTAMP1T(5, 64); CSA(5);
        const uint32_t mu = (up0 ? 0xffffu : 0u) | (up1 ? 0xffff0000u : 0u);
        uint32_t ob[10][2];
#pragma unroll
        for (int P = 0; P < 2; P++) {
            float os[2][4];
#pragma unroll
            for (int e = 0; e < 2; e++) {
                const int h = 2 * P + e;
                const float i0 = rcp_apx(sum[h][0]), i1 = rcp_apx(sum[h][1]);
                const uint32_t w0 = pack2(p[h][0] * rk[0] * i0, p[h][1] * rk[1] * i0), w1 = pack2(p[h][2] * rk[2] * i1, p[h][3] * rk[3] * i1);
#pragma unroll
                for (int dt = 0; dt < 3; dt++) {
                    const int j = 5 * P + (dt < 2 ? 3 * e + dt : 2);
                    float o[4] = {0.f, 0.f, 0.f, 0.f};
                    mma_bf16(o, w0 & ~mu, w1 & mu, 0u, w1 & ~mu, vb[j][0], vb[j][1]);
                    mma_bf16_k8(o, w0 & mu, 0u, vp[j]);
                    if (dt < 2) { ob[j][0] = pack2(o[0], o[1]); ob[j][1] = pack2(o[2], o[3]); }
                    else { os[e][0] = o[0]; os[e][1] = o[1]; os[e][2] = o[2]; os[e][3] = o[3]; }
                }
            }
#pragma unroll
            for (int k = 0; k < 4; k++) os[0][k] = t < 2 ? os[0][k] : os[1][k];
            ob[5 * P + 2][0] = pack2(os[0][0], os[0][1]); ob[5 * P + 2][1] = pack2(os[0][2], os[0][3]);
        }
        const uint32_t sl = sbase + (wg ? A1_SM_A1 : A1_SM_A0);
        const uint32_t o0 = (warp & 3) * 2048 + g * 64 + ((t ^ (g >> 1)) << 4), o1 = 8192 + (warp & 3) * 512 + g * 32 + ((t ^ ((g >> 2) << 1)) << 3);
        CSA(15);
#pragma unroll
        for (int j = 0; j < 10; j++) asm volatile("" : "+r"(ob[j][0]), "+r"(ob[j][1]) :: "memory");
        if (wg == 0 && lane == 0) mbar_arrive(bar_pv);
        mbar_wait(bar_done, 0);
        if (wg == 0) mbar_wait(bar_kvf, 0);
#pragma unroll
        for (int h = 0; h < 2; h++) {
            asm volatile("st.shared.v4.u32 [%0], {%1,%2,%3,%4};" ::"r"(sl + o0 + h * 1024), "r"(ob[0][h]), "r"(ob[1][h]), "r"(ob[2][h]), "r"(ob[3][h]) : "memory");
            asm volatile("st.shared.v4.u32 [%0], {%1,%2,%3,%4};" ::"r"(sl + o0 + h * 1024 + 512), "r"(ob[4][h]), "r"(ob[5][h]), "r"(ob[6][h]), "r"(ob[7][h]) : "memory");
            asm volatile("st.shared.v2.u32 [%0], {%1,%2};" ::"r"(sl + o1 + h * 256), "r"(ob[8][h]), "r"(ob[9][h]) : "memory");
        }
        if (warp > 4 && lane == 0) mbar_arrive(bars + 384 + 8 * warp);
        fence_async_smem();
        __syncwarp();
        TSTAMP1T(4, 64); CSA(6);
        TSTAMP1(1);
        TSTAMP2(1);
        const unsigned char* ot = reinterpret_cast<const unsigned char*>(of) + mb * 163840 + wg * 10240;
        if (lane == 0) {
            asm volatile("cp.async.bulk.global.shared::cta.bulk_group [%0], [%1], 2048;" ::"l"(ot + hg * 20480 + (warp & 3) * 2048), "r"(sl + (warp & 3) * 2048) : "memory");
            asm volatile("cp.async.bulk.global.shared::cta.bulk_group [%0], [%1], 512;" ::"l"(ot + hg * 20480 + 8192 + (warp & 3) * 512), "r"(sl + 8192 + (warp & 3) * 512) : "memory");
            asm volatile("cp.async.bulk.commit_group;" ::: "memory");
            asm volatile("cp.async.bulk.wait_group 0;" ::: "memory");
            asm volatile(A1_FRED " [%0], 1;" ::"l"(reinterpret_cast<uint32_t*>(rsum + 2 * SEQ) + (((layer * 16 + mb) * 2 + wg) * 8 + hg) * FSTR) : "memory");
            DBGC(4 + warp);
        }
        TSTAMP4(11); CSA(7);
        float ac2[40];
        const uint64_t db0 = make_desc(sbase, 1024, 256, 3), db1 = make_desc(sbase + 10240, 512, 256, 3), da0 = make_desc(sl, 16, 1024, 2), da1 = make_desc(sl + 8192, 16, 256, 3);
        const uint32_t o7 = wg ? 640 : (A1_SM_W0 - A1_SM_A0) >> 4;
        const uint32_t trow = ((lane & 7) + 8 * (lane >> 4)) * 128 + (((2 * (warp & 3) + ((lane >> 3) & 1)) ^ (lane & 7)) << 4);
        uint32_t xr[10][2];
        mbar_wait(bar_f2 + 64 * wg + 64, 0);
        if (layer == 0) {
#pragma unroll
            for (int j = 0; j < 10; j += 2) ldsm_x4(&xr[j][0], sl + 51200 + (16 * (warp & 3) + (lane & 15)) * 160 + (lane >> 4) * 16 + 16 * j);
        } else {
#pragma unroll
            for (int j = 0; j < 10; j += 2) ldsm_x4_t(&xr[j][0], sl + 51200 + trow + 1024 * j);
        }
        const uint32_t ri = __shfl_sync(~0u, layer * SEQ + (wg * 2 + ((g >> 1) & 1)) * 512 + (mb * 16 + 4 * (warp & 3) + (g >> 2)) * 2 + (g & 1), lane);
        mbar_wait(bar_wo, 0);
        if (wg) asm volatile("bar.sync 2, 128;" ::: "memory"); else asm volatile("bar.sync 1, 128;" ::: "memory");
        if (wg) mbar_wait(bar_pv, 0);
        TSTAMP2(2); CSA(8);
#pragma unroll
        for (int q = 0; q < 8; q++) {
            uint32_t bo = wo_off(0) >> 4;
            if (q) {
                mbar_wait(bar_f2 + 64 * wg + 8 * q, 0);
                asm volatile("ld.shared.u32 %0, [%1];" : "=r"(bo) : "r"(que + 32 * wg + 4 * q) : "memory");
                bo = __shfl_sync(~0u, bo, 0);
                TSTAMP4(q);
                if (q % 3 == 1) CSA(9 + q / 3);
                if (q == 1 && (tid & 127) == 0) DBGC(29 + 8 * wg);
            }
            wgmma_fence();
#pragma unroll
            for (int j = 0; j < 5; j++) wgmma_n80(ac2, (j < 4 ? da0 : da1) + (q == 7 ? o7 : 0u) + (uint64_t)((q < 6 ? q * 640 : 0) + (j & 2) * 16 + (j & 1) * 2), (j < 4 ? db0 : db1) + bo + (uint64_t)((j & 2) * 160 + (j & 1) * 32), j || q);
            wgmma_commit();
            if (q == 0) {
                wgmma_wait<0>();
                if ((tid & 127) == 0) { mbar_arrive(bar_e2 + 16 * wg); mbar_arrive(bar_e2 + 8); }
            }
            if (q == 2 && wg) {
                wgmma_wait<1>();
                if (tid == 128) mbar_arrive(bar_e2 + 24);
            }
        }
        if ((tid & 127) == 0) DBGC(28 + wg * 8 + 7);
        TSTAMP2(3);
        wgmma_wait<0>();
        TSTAMP2(4); CSA(12);
        if (__any_sync(~0u, ac2[0] != ac2[0] || ac2[2] != ac2[2])) {
#pragma unroll
            for (int i = 0; i < 40; i++) ac2[i] = 0.f;
            uint32_t a[20], an[20];
            auto lda = [&](uint32_t (&r)[20], int h) {
#pragma unroll
                for (int u = 0; u < 4; u++)
                    asm volatile("ld.relaxed.gpu.global.v4.u32 {%0,%1,%2,%3}, [%4];" : "=r"(r[4 * u]), "=r"(r[4 * u + 1]), "=r"(r[4 * u + 2]), "=r"(r[4 * u + 3]) : "l"(ot + h * 20480 + o0 + u * 512) : "memory");
#pragma unroll
                for (int u = 0; u < 2; u++)
                    asm volatile("ld.relaxed.gpu.global.v2.u32 {%0,%1}, [%2];" : "=r"(r[16 + 2 * u]), "=r"(r[17 + 2 * u]) : "l"(ot + h * 20480 + o1 + u * 256) : "memory");
            };
            lda(an, 0);
#pragma unroll 5
            for (int k = lane; k < WOB / 16; k += 32)
                reinterpret_cast<uint4*>(stg + (sl - sbase))[k] = __ldcg(reinterpret_cast<const uint4*>(wo + hg * 8 * WOB) + k);
            __syncwarp();
#pragma unroll 1
            for (int h = 0; h < 8; h++) {
#pragma unroll 1
                for (int it = 0; it < SPIN_MAX; it++) {
                    uint32_t m = 0;
#pragma unroll
                    for (int k = 0; k < 20; k += 2) m = __vimax3_u32(m, an[k], an[k + 1]);
                    if (!__any_sync(~0u, m == ~0u)) break;
                    lda(an, h);
                }
#pragma unroll
                for (int k = 0; k < 20; k++) a[k] = an[k];
                lda(an, min(h + 1, 7));
                const uint32_t bp = h == hg ? sl : sbase + wo_off(h + (h < hg));
                const int r0 = 8 * ((lane & 7) >> 1) + 2 * (lane >> 3) + (lane & 1), r2 = 4 * ((lane & 7) >> 1) + 2 * ((lane >> 3) & 1) + (lane & 1);
#pragma unroll
                for (int n = 0; n < 10; n++) {
                    uint32_t b[12];
                    ldsm_x4_t(b, bp + (n >> 1) * 1024 + r0 * 32 + (((n ^ (r0 >> 2)) & 1) << 4));
                    ldsm_x4_t(b + 4, bp + 5120 + (n >> 1) * 1024 + r0 * 32 + (((n ^ (r0 >> 2)) & 1) << 4));
                    ldsm_x4_t(b + 8, bp + 10240 + (n >> 1) * 512 + r2 * 32 + (((n ^ (r2 >> 2)) & 1) << 4));
                    mma_bf16(ac2 + 4 * n, a[0], a[8], a[1], a[9], b[0], b[1]); mma_bf16(ac2 + 4 * n, a[2], a[10], a[3], a[11], b[2], b[3]);
                    mma_bf16(ac2 + 4 * n, a[4], a[12], a[5], a[13], b[4], b[5]); mma_bf16(ac2 + 4 * n, a[6], a[14], a[7], a[15], b[6], b[7]);
                    mma_bf16(ac2 + 4 * n, a[16], a[18], a[17], a[19], b[8], b[9]);
                }
            }
        }
#pragma unroll
        for (int j = 0; j < 10; j++)
#pragma unroll
            for (int hh = 0; hh < 2; hh++) {
                const uint32_t a = pack2(ac2[4 * j + 2 * hh], ac2[4 * j + 2 * hh + 1]);
                const __nv_bfloat162 r = __hadd2_rn(*reinterpret_cast<const __nv_bfloat162*>(&xr[j][hh]), *reinterpret_cast<const __nv_bfloat162*>(&a));
                xr[j][hh] = *reinterpret_cast<const uint32_t*>(&r);
            }
        const uint32_t so = sl + 30720;
#pragma unroll
        for (int j = 0; j < 10; j += 2) stsm_x4_t(so + trow + 1024 * j, xr[j][0], xr[j][1], xr[j + 1][0], xr[j + 1][1]);
        if (wg) asm volatile("bar.sync 2, 128;" ::: "memory"); else asm volatile("bar.sync 1, 128;" ::: "memory");
        TSTAMP2(5); CSA(13);
        if ((tid & 127) == 0) {
            fence_async_smem();
            asm volatile("cp.async.bulk.tensor.2d.global.shared::cta.bulk_group [%0, {%1, %2}], [%3];" ::"l"(&tmX1), "r"(mb * 128 + 64 * wg), "r"(hg * 80), "r"(so) : "memory");
            asm volatile("cp.async.bulk.commit_group;" ::: "memory");
        }
        __syncwarp();
        const float p0 = *(volatile const float*)&rw[g].x, p1 = *(volatile const float*)&rw[g + 8].x;
        float s[3][4] = {};
        const uint32_t pp[2] = {__byte_perm(__float_as_uint(p0), 0, 0x3232), __byte_perm(__float_as_uint(p1), 0, 0x3232)};
#pragma unroll
        for (int j = 0; j < 10; j += 2) {
            const uint32_t d0 = sub2(xr[j][0], pp[0]), d1 = sub2(xr[j][1], pp[1]), d2 = sub2(xr[j + 1][0], pp[0]), d3 = sub2(xr[j + 1][1], pp[1]);
            mma_bf16(s[0], xr[j][0], xr[j][1], xr[j + 1][0], xr[j + 1][1], 0x3f803f80u, 0x3f803f80u);
            mma_bf16(s[1], d0, d1, d2, d3, d0, d2);
            mma_bf16(s[2], d0, d1, d2, d3, d1, d3);
        }
        if (t == (g >> 1)) {
            float2* rp = rsum + ri;
            asm volatile("red.relaxed.gpu.global.add.v2.f32 [%0], {%1, %2};" ::"l"(rp), "f"(fmaf(-80.f, p0, s[0][0])), "f"((g & 1) ? s[1][1] : s[1][0]) : "memory");
            asm volatile("red.relaxed.gpu.global.add.v2.f32 [%0], {%1, %2};" ::"l"(rp + 4), "f"(fmaf(-80.f, p1, s[0][2])), "f"((g & 1) ? s[2][3] : s[2][2]) : "memory");
        }
        asm volatile("cp.async.bulk.wait_group.read 0;" ::: "memory");
        TSTAMP2(6); CSA(14); CSA_END;
        if (tid == 0) DBGC(63);
        if (tid == 128) DBGC(28);
        if (tid == 0) DBGCAL(2);
        GSTAMP(g_tim1, 14);
        SPAN(1 + 4 * layer, 3);
    }
#undef layer
}

static int h_nsm;
static void* h_sym[11];
static TileTab h_tab[2];
static CUtensorMap h_tmX0, h_tmX1, h_tmR0, h_tmR1, h_tmX1st, h_tmOut;
static KgMaps h_tmW;
typedef CUresult (*PFN_encodeTiled)(CUtensorMap*, CUtensorMapDataType, cuuint32_t, void*, const cuuint64_t*, const cuuint64_t*,
                                    const cuuint32_t*, const cuuint32_t*, CUtensorMapInterleave, CUtensorMapSwizzle,
                                    CUtensorMapL2promotion, CUtensorMapFloatOOBfill);
static void make_tmap(CUtensorMap* tm, const void* ptr, uint64_t cols, uint64_t rows, uint32_t bc, uint32_t br, CUtensorMapSwizzle sw, uint64_t pitch = 0, uint64_t hi = 0, uint32_t bh = 2) {
    static PFN_encodeTiled fn = nullptr;
    if (!fn) {
        void* p = nullptr; cudaDriverEntryPointQueryResult qr;
        cudaGetDriverEntryPoint("cuTensorMapEncodeTiled", &p, cudaEnableDefault, &qr);
        fn = (PFN_encodeTiled)p;
    }
    if (br == 0) {
        cuuint64_t dims[5] = {16, 2, rows / 8, 4, cols / 16}; cuuint64_t strides[4] = {cols * 2, cols * 16, cols * 4, 32};
        cuuint32_t box[5] = {16, 2, bc, 4, 5}; cuuint32_t es[5] = {1, 1, 1, 1, 1};
        fn(tm, CU_TENSOR_MAP_DATA_TYPE_BFLOAT16, 5, const_cast<void*>(ptr), dims, strides, box, es, CU_TENSOR_MAP_INTERLEAVE_NONE, sw,
           CU_TENSOR_MAP_L2_PROMOTION_L2_128B, CU_TENSOR_MAP_FLOAT_OOB_FILL_NONE);
        return;
    }
    if (hi == 16) {
        cuuint64_t dims[4] = {16, 32, 120, 20}; cuuint64_t strides[3] = {3840, 32, 32 * 3840};
        cuuint32_t box[4] = {16, 32, 5, 2}; cuuint32_t es[4] = {1, 1, 1, 1};
        fn(tm, CU_TENSOR_MAP_DATA_TYPE_BFLOAT16, 4, const_cast<void*>(ptr), dims, strides, box, es, CU_TENSOR_MAP_INTERLEAVE_NONE, sw,
           CU_TENSOR_MAP_L2_PROMOTION_L2_128B, CU_TENSOR_MAP_FLOAT_OOB_FILL_NONE);
        return;
    }
    if (bh == 0) {
        cuuint64_t dims[5] = {64, 64, 2, 16, 10}; cuuint64_t strides[4] = {pitch * 2, hi * 2, cols * 2, rows * 2};
        cuuint32_t box[5] = {64, 64, 2, 1, 1}; cuuint32_t es[5] = {1, 1, 1, 1, 1};
        fn(tm, CU_TENSOR_MAP_DATA_TYPE_BFLOAT16, 5, const_cast<void*>(ptr), dims, strides, box, es, CU_TENSOR_MAP_INTERLEAVE_NONE, sw,
           CU_TENSOR_MAP_L2_PROMOTION_L2_128B, CU_TENSOR_MAP_FLOAT_OOB_FILL_NONE);
        return;
    }
    if (hi) {
        cuuint64_t dims[3] = {cols, rows, hi == 64 ? 32u : 2u}; cuuint64_t strides[2] = {pitch * 2, hi * 2};
        cuuint32_t box[3] = {bc, br, bh}; cuuint32_t es[3] = {1, 1, 1};
        fn(tm, CU_TENSOR_MAP_DATA_TYPE_BFLOAT16, 3, const_cast<void*>(ptr), dims, strides, box, es, CU_TENSOR_MAP_INTERLEAVE_NONE, sw,
           CU_TENSOR_MAP_L2_PROMOTION_L2_128B, CU_TENSOR_MAP_FLOAT_OOB_FILL_NONE);
        return;
    }
    cuuint64_t dims[2] = {cols, rows}; cuuint64_t strides[1] = {(pitch ? pitch : cols) * 2};
    cuuint32_t box[2] = {bc, br}; cuuint32_t es[2] = {1, 1};
    fn(tm, CU_TENSOR_MAP_DATA_TYPE_BFLOAT16, 2, const_cast<void*>(ptr), dims, strides, box, es, CU_TENSOR_MAP_INTERLEAVE_NONE, sw,
       CU_TENSOR_MAP_L2_PROMOTION_L2_128B, CU_TENSOR_MAP_FLOAT_OOB_FILL_NONE);
}
template <typename... Args>
static void launch_pdl(void (*kern)(Args...), int grid, int block, int smem, Args... args) {
    cudaLaunchConfig_t cfg = {};
    cfg.gridDim = dim3(grid); cfg.blockDim = dim3(block); cfg.dynamicSmemBytes = smem; cfg.stream = cudaStreamPerThread;
    cudaLaunchAttribute at[1];
    at[0].id = cudaLaunchAttributeProgrammaticStreamSerialization; at[0].val.programmaticStreamSerializationAllowed = 1;
    cfg.attrs = at; cfg.numAttrs = 1;
    cudaLaunchKernelEx(&cfg, kern, args...);
}
static void launch_stage(int k, void* const* d_in, void* d_out) {
    const Par par = {k > 1 ? nullptr : (const bf16*)d_in[4], (const bf16*)d_in[5], (const bf16*)d_in[6], (const bf16*)d_in[7], (const bf16*)d_in[8], (const bf16*)d_in[9], k > 1, 0, (const bf16*)d_in[0],
                     (uint4*)h_sym[4], (uint4*)h_sym[2], (uint4*)h_sym[6], (uint4*)h_sym[3], (uint4*)h_sym[0], (float*)h_sym[5], (uint4*)h_sym[1], (const bf16*)d_in[1], (const bf16*)d_in[2]};
    auto a1 = h_nsm == 132 ? a1_kernel<true> : a1_kernel<false>;
    switch (k) {
        case 1: a1<<<h_nsm, A1_THREADS, A1_SMEM, cudaStreamPerThread>>>(par, h_tmX0, h_tmR0, h_tmX1st, h_tmW, h_tab[0]); break;
        case 3: launch_pdl(conv_kernel, DM / CV_CPB, CV_THREADS, CV_SMEM, 0, (const uint4*)h_sym[7], (const float4*)h_sym[4], (const bf16*)h_sym[8], (bf16*)h_sym[9], (const uint4*)h_sym[0], h_tmOut); break;
        case 5: launch_pdl(a1, h_nsm, A1_THREADS, A1_SMEM, par, h_tmX1, h_tmR1, h_tmX1st, h_tmW, h_tab[1]); break;
        case 7: launch_pdl(conv_kernel, DM / CV_CPB, CV_THREADS, CV_SMEM, 1, (const uint4*)h_sym[7] + SEQ / 8, (const float4*)h_sym[4] + SEQ / 2, (const bf16*)h_sym[8], (bf16*)h_sym[10], (const uint4*)h_sym[0], h_tmOut); break;
        default: break;
    }
}
static int n_stage_kernels() { return 9; }
static const char* stage_name(int k) { const char* n[] = {"kgen", "a1", "a2", "conv", "tr", "a1", "a2", "conv", "tr"}; return n[k]; }

extern "C" void kernel_launch(void* const* d_in, const int* in_sizes, int n_in, void* d_out, int out_size) {
    (void)in_sizes; (void)n_in; (void)out_size;
    static const void *p_in = nullptr, *p_w1 = nullptr, *p_w2 = nullptr, *p_out = nullptr;
    if (p_in != d_in[0] || p_w1 != d_in[1] || p_w2 != d_in[2] || p_out != d_out) {
        cudaFuncSetAttribute(conv_kernel, cudaFuncAttributeMaxDynamicSharedMemorySize, CV_SMEM);
        cudaFuncSetAttribute(a1_kernel<true>, cudaFuncAttributeMaxDynamicSharedMemorySize, A1_SMEM);
        cudaFuncSetAttribute(a1_kernel<false>, cudaFuncAttributeMaxDynamicSharedMemorySize, A1_SMEM);
        int dev; cudaGetDevice(&dev); cudaDeviceGetAttribute(&h_nsm, cudaDevAttrMultiProcessorCount, dev);
        if (h_nsm != 132) h_nsm = 128;
        cudaGetSymbolAddress(&h_sym[0], g_tap); cudaGetSymbolAddress(&h_sym[1], g_wq); cudaGetSymbolAddress(&h_sym[2], g_wo);
        cudaGetSymbolAddress(&h_sym[3], g_halo); cudaGetSymbolAddress(&h_sym[4], g_sum); cudaGetSymbolAddress(&h_sym[5], g_csp); cudaGetSymbolAddress(&h_sym[6], g_of);
        cudaGetSymbolAddress(&h_sym[7], g_piv); cudaGetSymbolAddress(&h_sym[8], g_x1T); cudaGetSymbolAddress(&h_sym[9], g_xcT); cudaGetSymbolAddress(&h_sym[10], g_yT);
        for (int i = 0; i < 264; i++) {
            const int s = i % 132, h = (s - 64) >> 1;
            const int t = h_nsm != 132 ? s : s < 64 ? ((s >> 1) & 7) * 16 + (s >> 4) * 2 + (s & 1) : s < 120 ? (1 + h % 7) * 16 + 8 + (h / 7) * 2 + (s & 1) : s < 124 ? 128 : s - 116;
            const int hg = (4 * (t >> 6) + (t & 3)) & 7;
            const uint64_t wp = (uint64_t)h_sym[1] + hg * 10 * WQ_STAGE;
            h_tab[i / 132].e[s] = make_uint4((uint32_t)wp, (uint32_t)(wp >> 32), ((t >> 2) & 15) | (i / 132) << 4 | hg << 8 | 5 * (hg >> 2) << 16 | (uint32_t)t << 24, 0);
        }
        void *px1, *px2;
        cudaGetSymbolAddress(&px1, g_x1T); cudaGetSymbolAddress(&px2, g_xcT);
        make_tmap(&h_tmX0, d_in[0], 128 * 640, 64, 64, 64, CU_TENSOR_MAP_SWIZZLE_128B, 1280, 640, 0);
        make_tmap(&h_tmX1, px2, 128, 64 * XCP, 64, 64, CU_TENSOR_MAP_SWIZZLE_128B, XCP, 64, 0);
        make_tmap(&h_tmR0, d_in[0], 640, 1024, 80, 64, CU_TENSOR_MAP_SWIZZLE_NONE, 1280, 640, 1);
        make_tmap(&h_tmR1, px2, 64, 640, 64, 80, CU_TENSOR_MAP_SWIZZLE_128B, XCP, 64, 1);
        make_tmap(&h_tmX1st, px1, 2048, 640, 64, 80, CU_TENSOR_MAP_SWIZZLE_128B, XCP);
        make_tmap(&h_tmW.q, d_in[1], 16, 640, 16, 32, CU_TENSOR_MAP_SWIZZLE_32B, 1920, 16, 5);
        make_tmap(&h_tmW.o, d_in[2], 640, 640, 4, 0, CU_TENSOR_MAP_SWIZZLE_32B);
        make_tmap(&h_tmW.t, d_in[2], 640, 640, 2, 0, CU_TENSOR_MAP_SWIZZLE_32B);
        make_tmap(&h_tmOut, d_out, 640, 1024, 80, 8, CU_TENSOR_MAP_SWIZZLE_NONE, 1280, 640, 1);
        p_in = d_in[0]; p_w1 = d_in[1]; p_w2 = d_in[2]; p_out = d_out;
    }
    for (int k = 0; k < n_stage_kernels(); k++) launch_stage(k, d_in, d_out);
}
```

```cpp
#include <cuda_runtime.h>
#include <cuda_bf16.h>
#include <cuda_fp16.h>
#include <stdint.h>
#include <cuda.h>

typedef __nv_bfloat16 bf16;

constexpr int SEQ = 2048;
constexpr int DM = 640;
constexpr int NMODE = 192;

__device__ __forceinline__ float bf2f(bf16 v) { return __bfloat162float(v); }
__device__ __forceinline__ float rbf(float v) {
    uint32_t r;
    asm("cvt.rn.bf16x2.f32 %0, %1, %2;" : "=r"(r) : "f"(v), "f"(0.f));
    return __uint_as_float(r);
}
__device__ __forceinline__ uint32_t pack2(float lo, float hi) {
    __nv_bfloat162 t = __floats2bfloat162_rn(lo, hi);
    return *reinterpret_cast<uint32_t*>(&t);
}
__device__ __forceinline__ void pdl_sync() {
    asm volatile("griddepcontrol.wait;" ::: "memory");
    asm volatile("griddepcontrol.launch_dependents;" ::: "memory");
}
__device__ __forceinline__ float sqrt_apx(float v) { float r; asm("sqrt.approx.ftz.f32 %0, %1;" : "=f"(r) : "f"(v)); return r; }
__device__ __forceinline__ float rcp_apx(float v) { float r; asm("rcp.approx.ftz.f32 %0, %1;" : "=f"(r) : "f"(v)); return r; }
__device__ __forceinline__ uint32_t smem_u32(const void* p) { return (uint32_t)__cvta_generic_to_shared(p); }

constexpr int TAPB = 2944, TAPE = 928;
__device__ __align__(128) uint4 g_tap[DM * TAPB / 16];
#define XPAD 64
constexpr int XCP = SEQ + XPAD;
__device__ __align__(128) bf16 g_x1T[DM * XCP];
__device__ __align__(128) bf16 g_xcT[DM * XCP];
__device__ __align__(128) uint4 g_of[128 * 1280];
constexpr int WQ_STAGE = 240 * 128, WOB = 80 * 160;
__device__ __align__(128) uint4 g_wq[8 * 10 * WQ_STAGE / 16];
__device__ __align__(128) uint4 g_wo[64 * WOB / 16];
__device__ __align__(128) uint4 g_xb[128 * 240];
__device__ __align__(16) float g_csp[10 * 1920];
#define FSTR 32
__device__ __align__(128) float2 g_sum[2 * SEQ + 256 * FSTR];
__device__ __align__(16) bf16 g_piv[2 * SEQ];
__device__ __align__(128) bf16 g_yT[DM * XCP];
__device__ uint32_t g_epoch;
__device__ __align__(16) unsigned long long g_rstat[SEQ];
__device__ __align__(128) uint4 g_halo[640 * 148];
__device__ __forceinline__ unsigned long long tagw(uint32_t payload, uint32_t tag) { return ((unsigned long long)tag << 32) | payload; }
__device__ __forceinline__ ulonglong2 ld_tag2(const ulonglong2* p) {
    ulonglong2 v;
    asm volatile("ld.relaxed.gpu.global.v2.u64 {%0, %1}, [%2];" : "=l"(v.x), "=l"(v.y) : "l"(p) : "memory");
    return v;
}
__device__ __forceinline__ bool tag_ok(ulonglong2 v, uint32_t tag) { return (uint32_t)(v.x >> 32) == tag && (uint32_t)(v.y >> 32) == tag; }
__device__ __forceinline__ uint32_t ld_epoch() { uint32_t v; asm volatile("ld.relaxed.gpu.global.u32 %0, [%1];" : "=r"(v) : "l"(&g_epoch) : "memory"); return v + 1; }
constexpr int SPIN_MAX = 1 << 20;
__device__ __align__(128) uint32_t g_started[11 * 32];
__device__ __forceinline__ void sm_started(int slot) { asm volatile("red.relaxed.gpu.global.add.u32 [%0], 1;" ::"l"(g_started + slot) : "memory"); }
__device__ __forceinline__ void publish(int slot) {
    asm volatile("fence.proxy.async.global;" ::: "memory");
    asm volatile("red.release.gpu.global.add.u32 [%0], 1;" ::"l"(g_started + slot) : "memory");
}
__device__ __forceinline__ void await_all(int slot, uint32_t want) {
#pragma unroll 1
    for (int it = 0; it < SPIN_MAX; it++) {
        uint32_t v;
        asm volatile("ld.acquire.gpu.global.u32 %0, [%1];" : "=r"(v) : "l"(g_started + slot) : "memory");
        if (__all_sync(~0u, (int)(v - want) >= 0)) break;
        __nanosleep(50);
    }
    asm volatile("fence.proxy.async.global;" ::: "memory");
}
__device__ __noinline__ void sm_idle(int slot) {
    if (threadIdx.x != 288) return;
    asm volatile("fence.acq_rel.gpu;" ::: "memory");
    asm volatile("fence.proxy.async.global;" ::: "memory");
    sm_started(slot);
    const uint32_t want = ld_epoch() * gridDim.x;
    pdl_sync();
#pragma unroll 1
    for (int it = 0; it < SPIN_MAX; it++) {
        uint32_t v;
        asm volatile("ld.relaxed.gpu.global.u32 %0, [%1];" : "=r"(v) : "l"(g_started + slot) : "memory");
        if ((int)(v - want) >= 0) break;
        __nanosleep(100);
    }
}
struct TileTab { uint4 e[132]; };
__device__ __forceinline__ bool elect() {
    uint32_t p;
    asm volatile("{\n.reg .pred p;\nelect.sync _|p, 0xffffffff;\nselp.b32 %0, 1, 0, p;\n}" : "=r"(p));
    return p;
}
#define DBG_SYMS
#define TSTAMP(i)
#define TSTAMP1(i)
#define TSTAMP1T(i, t)
#define TSTAMP1X(i, t)
#define SPAN(k, i)
#define GSTAMP(arr, i)
#define TSTAMP2(i)
#define TSTAMP3(i)
#define TSTAMP4(i)
#define TSTAMPK(i, t)
#define TSTAMPC(i)
#define DBGC(i)
#define DBGV(i, v)
#define DBGCAL(i)

#define CSK(i)
#define CSK_END
#define CSA(i)
#define CSA_END
#define CST(i)
#define CST_END
#define CST_EXTRA 0
__device__ __forceinline__ void mma_bf16(float* d, uint32_t a0, uint32_t a1, uint32_t a2, uint32_t a3, uint32_t b0, uint32_t b1) {
    asm volatile("mma.sync.aligned.m16n8k16.row.col.f32.bf16.bf16.f32 {%0,%1,%2,%3}, {%4,%5,%6,%7}, {%8,%9}, {%0,%1,%2,%3};"
                 : "+f"(d[0]), "+f"(d[1]), "+f"(d[2]), "+f"(d[3]) : "r"(a0), "r"(a1), "r"(a2), "r"(a3), "r"(b0), "r"(b1));
}
__device__ __forceinline__ void mma_bf16_k8(float* d, uint32_t a0, uint32_t a1, uint32_t b0) {
    asm volatile("mma.sync.aligned.m16n8k8.row.col.f32.bf16.bf16.f32 {%0,%1,%2,%3}, {%4,%5}, {%6}, {%0,%1,%2,%3};"
                 : "+f"(d[0]), "+f"(d[1]), "+f"(d[2]), "+f"(d[3]) : "r"(a0), "r"(a1), "r"(b0));
}
__device__ __forceinline__ void ldsm_x4(uint32_t* r, uint32_t addr) {
    asm volatile("ldmatrix.sync.aligned.m8n8.x4.shared.b16 {%0,%1,%2,%3}, [%4];"
                 : "=r"(r[0]), "=r"(r[1]), "=r"(r[2]), "=r"(r[3]) : "r"(addr));
}

__device__ __forceinline__ void ldsm_x4_t(uint32_t* r, uint32_t addr) {
    asm volatile("ldmatrix.sync.aligned.m8n8.x4.trans.shared.b16 {%0,%1,%2,%3}, [%4];"
                 : "=r"(r[0]), "=r"(r[1]), "=r"(r[2]), "=r"(r[3]) : "r"(addr));
}
__device__ __forceinline__ void mbar_init(uint32_t bar, int count) { asm volatile("mbarrier.init.shared::cta.b64 [%0], %1;" ::"r"(bar), "r"(count)); }
__device__ __forceinline__ void mbar_arrive(uint32_t bar) { asm volatile("mbarrier.arrive.shared::cta.b64 _, [%0];" ::"r"(bar) : "memory"); }
__device__ __forceinline__ void mbar_wait(uint32_t bar, uint32_t parity) {
    asm volatile("{\n.reg .pred p;\nWAIT_LOOP:\n"
                 "mbarrier.try_wait.parity.shared::cta.b64 p, [%0], %1;\n"
                 "@p bra.uni WAIT_DONE;\nbra.uni WAIT_LOOP;\nWAIT_DONE:\n}" ::"r"(bar), "r"(parity) : "memory");
}

__device__ __forceinline__ void mbar_expect_tx(uint32_t bar, uint32_t bytes) {
    asm volatile("mbarrier.arrive.expect_tx.shared::cta.b64 _, [%0], %1;" ::"r"(bar), "r"(bytes) : "memory");
}
__device__ __forceinline__ void tma_load_2d(uint32_t dst, const void* tmap, int c0, int c1, uint32_t bar) {
    asm volatile("cp.async.bulk.tensor.2d.shared::cluster.global.mbarrier::complete_tx::bytes [%0], [%1, {%3, %4}], [%2];"
                 ::"r"(dst), "l"(tmap), "r"(bar), "r"(c0), "r"(c1) : "memory");
}
__device__ __forceinline__ void tma_load_3d(uint32_t dst, const void* tmap, int c0, int c1, int c2, uint32_t bar) {
    asm volatile("cp.async.bulk.tensor.3d.shared::cluster.global.mbarrier::complete_tx::bytes [%0], [%1, {%3, %4, %5}], [%2];"
                 ::"r"(dst), "l"(tmap), "r"(bar), "r"(c0), "r"(c1), "r"(c2) : "memory");
}
__device__ __forceinline__ void fence_async_smem() { asm volatile("fence.proxy.async.shared::cta;" ::: "memory"); }
__device__ __forceinline__ void bulk_load(uint32_t dst, const void* src, uint32_t bytes, uint32_t bar) {
    asm volatile("cp.async.bulk.shared::cluster.global.mbarrier::complete_tx::bytes [%0], [%1], %2, [%3];"
                 ::"r"(dst), "l"(src), "r"(bytes), "r"(bar) : "memory");
}
__device__ __forceinline__ void stsm_x4(uint32_t addr, uint32_t r0, uint32_t r1, uint32_t r2, uint32_t r3) {
    asm volatile("stmatrix.sync.aligned.m8n8.x4.shared.b16 [%0], {%1,%2,%3,%4};" ::"r"(addr), "r"(r0), "r"(r1), "r"(r2), "r"(r3) : "memory");
}
__device__ __forceinline__ void stsm_x4_t(uint32_t addr, uint32_t r0, uint32_t r1, uint32_t r2, uint32_t r3) {
    asm volatile("stmatrix.sync.aligned.m8n8.x4.trans.shared.b16 [%0], {%1,%2,%3,%4};" ::"r"(addr), "r"(r0), "r"(r1), "r"(r2), "r"(r3) : "memory");
}
__device__ __forceinline__ void prefetch_tmap(const void* tmap) { asm volatile("prefetch.tensormap [%0];" ::"l"(tmap) : "memory"); }

__device__ __forceinline__ float2 cexp_at(float wr2, float wi, float p) {
    float er;
    asm("ex2.approx.ftz.f32 %0, %1;" : "=f"(er) : "f"(wr2 * p));
    float th = wi * p;
    const float k = rintf(th * 0.15915494309189535f);
    th = fmaf(k, -6.2831854820251465f, th);
    th = fmaf(k, 1.7484555314695172e-7f, th);
    return make_float2(er * __cosf(th), er * __sinf(th));
}
__device__ __forceinline__ float2 cmul(float2 a, float2 b) {
    return make_float2(fmaf(a.x, b.x, -a.y * b.y), fmaf(a.x, b.y, a.y * b.x));
}
__device__ __forceinline__ float2 csqr(float2 a) { return make_float2(fmaf(a.x, a.x, -a.y * a.y), (a.x + a.x) * a.y); }
__device__ __forceinline__ uint32_t packh(float2 v) {
    uint32_t r;
    asm("cvt.rn.f16x2.f32 %0, %1, %2;" : "=r"(r) : "f"(v.y), "f"(v.x));
    return r;
}
__device__ __forceinline__ uint2 packr(float2 v) { return make_uint2(packh(v), packh(make_float2(-v.y, v.x))); }
__device__ __forceinline__ uint32_t hcmul(uint32_t a, uint2 b) {
    const __half2 x = *reinterpret_cast<const __half2*>(&a);
    const __half2 r = __hfma2(__high2half2(x), *reinterpret_cast<const __half2*>(&b.y), __hmul2(__low2half2(x), *reinterpret_cast<const __half2*>(&b.x)));
    return *reinterpret_cast<const uint32_t*>(&r);
}

struct Par { const bf16 *logA, *Aim, *Cre, *Cim, *logdt, *dsk; int layer, pad; const bf16* x; uint4 *sum, *wop, *of, *halo, *tap; float* csp; uint4* wq; const bf16 *wqkv, *wo; };
struct KgMaps { CUtensorMap q, o, t; };

__device__ __forceinline__ void bulk_prefetch(const void* p, uint32_t bytes) { asm volatile("cp.async.bulk.prefetch.L2.global [%0], %1;" ::"l"(p), "r"(bytes) : "memory"); }
__device__ __forceinline__ void bulk_store(void* dst, uint32_t src, uint32_t bytes) { asm volatile("cp.async.bulk.global.shared::cta.bulk_group [%0], [%1], %2;" ::"l"(dst), "r"(src), "r"(bytes) : "memory"); }
__device__ __forceinline__ void kgen_first(const Par& in, const KgMaps& tm, const uint32_t b0, const uint32_t wbar, const bool one) {
    const uint32_t blk = blockIdx.x, sec = (blk >= 40) + (blk >= 80), it = (blk >> 3) - 5 * sec, up = (blk >> 2) & 1, hi = blk >> 6;
    auto fetch = [&](int h) {
        if (blk < 120) asm volatile("cp.async.bulk.tensor.4d.shared::cluster.global.mbarrier::complete_tx::bytes [%0], [%1, {%3, %3, %4, %5}], [%2];"
                                    ::"r"(b0 + 10240 * h), "l"(&tm.q), "r"(wbar + 8 * h), "r"(0), "r"(sec * 40 + (blk & 7) * 5), "r"(2 * it + 10 * (up ^ h)) : "memory");
    };
    auto fetch_o = [&](int i) {
        asm volatile("cp.async.bulk.tensor.5d.shared::cluster.global.mbarrier::complete_tx::bytes [%0], [%1, {%3, %3, %4, %3, %5}], [%2];"
                     ::"r"(b0 + 20480 + i * 5120), "l"(&tm.o + i), "r"(wbar + 16), "r"(0), "r"((blk & 7) * 10 + (hi + i) * 4), "r"(((blk >> 3) & 7) * 5) : "memory");
    };
    if (one) {
#pragma unroll
        for (int i = 0; i < 3; i++) mbar_init(wbar + 8 * i, 1);
        asm volatile("fence.mbarrier_init.release.cluster;" ::: "memory");
        fetch(0);
    }
    __syncwarp();
    if (blk >> 20) __trap();
    if (one) {
        bulk_prefetch(in.wqkv + blk * 9600, 19200);
        fetch(1);
        bulk_prefetch(in.wo + blk * 3200, 6400);
        fetch_o(0);
        if (hi) fetch_o(1);
        mbar_expect_tx(wbar, 10240); mbar_expect_tx(wbar + 8, 10240); mbar_expect_tx(wbar + 16, 5120 + hi * 2560);
        bulk_prefetch(in.x + blk * 10240, 20480);
    }
}
__device__ __forceinline__ void kgen_side(const Par& in, const uint32_t b0, const uint32_t wbar) {
    const uint32_t blk = blockIdx.x, sec = (blk >= 40) + (blk >= 80), it = (blk >> 3) - 5 * sec, cg = (blk >> 3) & 7, hb = blk & 7;
    unsigned char* dst = reinterpret_cast<unsigned char*>(in.wq) + (hb * 10 + it) * WQ_STAGE + sec * 5120;
    if (blk < 120) {
        mbar_wait(wbar, 0);
        CSK(2);
        bulk_store(dst, b0, 5120); bulk_store(dst + 15360, b0 + 5120, 5120);
        mbar_wait(wbar + 8, 0);
        CSK(3);
        bulk_store(dst + 5 * WQ_STAGE, b0 + 10240, 5120); bulk_store(dst + 5 * WQ_STAGE + 15360, b0 + 15360, 5120);
        asm volatile("cp.async.bulk.commit_group;" ::: "memory");
        asm volatile("cp.async.bulk.wait_group 0;" ::: "memory");
        CSK(4);
        publish(96 + 32 * hb);
        CSK(5);
    }
    if (blk < 128) {
        mbar_wait(wbar + 16, 0);
        bulk_store(reinterpret_cast<unsigned char*>(in.wop) + (cg * 8 + (hb == cg ? 0 : hb + (hb < cg))) * WOB + (blk >> 6) * 5120, b0 + 20480, blk < 64 ? 5120 : 7680);
        asm volatile("cp.async.bulk.commit_group;" ::: "memory");
    }
}
__device__ __forceinline__ void kgen_sums(const Par& in, const uint32_t b0, const int h) {
    const int lane = threadIdx.x & 31, blk = blockIdx.x;
    if (blk < 120) {
        float cs[5][4] = {};
#pragma unroll
        for (int a = 0; a < 4; a++)
#pragma unroll
            for (int j = 0; j < 5; j++) {
                uint32_t w[4];
                ldsm_x4_t(w, b0 + h * 10240 + j * 1024 + ((lane >> 4) * 8 + (lane & 7)) * 32 + ((((lane >> 3) ^ (lane >> 2)) & 1) << 4) + (a >> 1) * 5120 + (a & 1) * 512);
                mma_bf16(cs[j], w[0], w[1], w[2], w[3], 0x3f803f80u, 0x3f803f80u);
            }
#pragma unroll
        for (int j = 0; j < 5; j++)
            if ((lane & 3) < 2) in.csp[(blk + 120 * h) * 80 + j * 16 + (lane >> 2) + 8 * (lane & 3)] = (lane & 3) ? cs[j][2] : cs[j][0];
    }
}
struct KgPar { uint32_t pw[4], ph[4], pdt, pdsk; };
__device__ __forceinline__ void kgen_load(const Par& in, const bf16* logA, const int w11, KgPar& k) {
    const uint32_t o = blockIdx.x * 480 + min(w11 * 48, w11 * 32 + 128), ow = o + (threadIdx.x & 31), oh = o + ow + (w11 < 8 ? 64 : 0);
    k.pdt = reinterpret_cast<const unsigned short*>(in.logdt)[ow / 96];
    k.pdsk = reinterpret_cast<const unsigned short*>(in.dsk)[ow / 96];
#pragma unroll
    for (int i = 0; i < 4; i++) {
        const bf16* p = i == 0 ? logA : i == 1 ? in.Aim : i == 2 ? in.Cre : in.Cim;
        k.pw[i] = reinterpret_cast<const uint32_t*>(p)[ow]; k.ph[i] = reinterpret_cast<const unsigned short*>(p)[oh];
    }
}
__device__ __forceinline__ void kgen_tables(const Par& in, uint4* tabs, const int w11, const KgPar& kp) {
    const int lane = threadIdx.x & 31, grp = min(w11 >> 1, 4), warp = w11 - 2 * grp;
    const int blk = blockIdx.x, d = blk * 5 + grp, tid = warp * 32 + lane;
    uint4* tab = tabs + grp * (2 * 256);
    const uint32_t *pw = kp.pw, *ph = kp.ph;
#pragma unroll
    for (int i = 0; i < 3; i++)
        if (i < 2 || w11 * 32 + lane < 36) asm volatile("st.global.v4.u32 [%0], {%1,%1,%1,%1};" ::"l"(in.halo + blk * 740 + w11 * 32 + lane + 352 * i), "r"(~0u));
    __syncwarp();
    if (w11 == 10) {
        if (lane < 16) in.sum[blk * 16 + lane] = make_uint4(0, 0, 0, 0);
        else if (lane < 20) reinterpret_cast<uint32_t*>(in.sum + 2048)[(blk * 4 + lane - 16) * FSTR] = 0;
    } else if (w11 > 1) asm volatile("bar.arrive 9, 352;" ::: "memory");
#pragma unroll
    for (int i = 0; i < 6; i++) tabs[w11 * 256 + 32 * i + lane] = make_uint4(0, 0, 0, 0);
    __syncwarp();
    CSK(1);
    const uint32_t tw = smem_u32(tabs) + w11 * 4096;
    const int g = lane >> 2, t = lane & 3;
    const int mt = lane >> 3, r = lane & 7;
    const uint32_t st1 = tw + mt * 1024 + r * 16, st2 = tw + (mt & 1) * 1024 + (mt >> 1) * 128 + ((r ^ (mt >> 1)) << 4), st3 = tw + 2048 + mt * 128 + ((r ^ mt) << 4);
    const uint32_t lda = tw + (mt & 1) * 1024 + r * 128 + (((mt >> 1) ^ r) << 4), ldb = tw + (mt >> 1) * 1024 + r * 128 + (((mt & 1) ^ r) << 4), ldc = tw + 2048 + r * 128 + ((mt ^ r) << 4);
    auto ldsm = [](uint32_t* v, uint32_t a) {
        asm volatile("ldmatrix.sync.aligned.m8n8.x4.shared.b16 {%0,%1,%2,%3}, [%4];" : "=r"(v[0]), "=r"(v[1]), "=r"(v[2]), "=r"(v[3]) : "r"(a) : "memory");
    };
    auto mma = [](float* c, const uint32_t* a, const uint32_t* b) {
        asm("mma.sync.aligned.m16n8k16.row.col.f32.f16.f16.f32 {%0,%1,%2,%3}, {%4,%5,%6,%7}, {%8,%9}, {%0,%1,%2,%3};"
            : "+f"(c[0]), "+f"(c[1]), "+f"(c[2]), "+f"(c[3]) : "r"(a[0]), "r"(a[1]), "r"(a[2]), "r"(a[3]), "r"(b[0]), "r"(b[1]));
    };
    asm volatile("st.shared.u32 [%0], %1;" ::"r"(tw + 3072), "r"(st1 ^ st2 ^ st3 ^ lda ^ ldb ^ ldc) : "memory");
    if (in.pad) __trap();
    const float dt = rbf(expf(__uint_as_float(kp.pdt << 16)));
    const uint32_t cm = __vmaxu2(__vmaxu2(pw[2] & 0x7fff7fffu, pw[3] & 0x7fff7fffu), __byte_perm(ph[2], ph[3], 0x5410) & 0x7fff7fffu);
    const int ex = min(max((int)(__float_as_uint(__uint_as_float(__reduce_max_sync(~0u, max(cm << 16, cm & 0xffff0000u))) * dt) >> 23), 20), 240);
    const float scale = __uint_as_float((uint32_t)(127 + 10 + 127 - ex) << 23), unscale = 2.0f * __uint_as_float((uint32_t)(ex - 10) << 23);
    float k2048 = 0.f;
    float acc[5][4] = {};
    uint32_t af[4][4] = {};
    auto rest = [&] {
        uint32_t b[4][4], c[8];
#pragma unroll
        for (int k = 0; k < 4; k++) {
            ldsm(b[k], ldb ^ (k << 5));
            if (!(k & 1)) ldsm(c + 2 * k, ldc ^ (k << 5));
        }
#pragma unroll
        for (int k = 0; k < 4; k++) { mma(acc[2], af[k], b[k]); mma(acc[3], af[k], b[k] + 2); mma(acc[4], af[k], c + 2 * k); }
    };
#pragma unroll 1
    for (uint32_t sel = 0x1076; sel < (grp < 4 ? 0x6000u : 0x4000u); sel += 0x2200) {
        rest();
        auto par = [&](int i) { return __uint_as_float(__byte_perm(pw[i], ph[i], sel)); };
        const float wr2 = -rbf(expf(par(0))) * dt * 1.4426950408889634f, wi = par(1) * dt;
        const float2 y1 = cexp_at(wr2, -wi, 1.f), w64 = cexp_at(wr2, wi, 64.f), y4 = csqr(csqr(y1)), z8 = csqr(make_float2(y4.x, -y4.y)), y128 = csqr(make_float2(w64.x, -w64.y));
        float2 h0 = make_float2(1.f, 0.f), g0 = make_float2(par(2) * dt * scale, -par(3) * dt * scale);
        const float2 v2 = csqr(y128), v3 = cmul(v2, y128), v4 = csqr(v2), v8 = csqr(v4), c8 = cmul(g0, v8);
        const uint2 z64 = packr(w64), v[8] = {make_uint2(packh(c8), 0u), packr(y128), packr(v2), packr(v3), packr(v4), packr(cmul(v4, y128)), packr(csqr(v3)), packr(cmul(v4, v3))};
        k2048 += fmaf(c8.x, v8.x, -c8.y * v8.y);
        uint32_t ge[4];
#pragma unroll
        for (int e = 0; e < 8; e++) {
            const uint32_t p = packh(h0), q = packh(g0);
            if (!(e & 1)) ge[e >> 1] = q;
            stsm_x4((st1 ^ (e << 4)) + e * 128, p, e ? hcmul(p, z64) : z64.x, q, hcmul(q, v[1]));
            if (e < 7) { h0 = e ? cmul(h0, z8) : z8; g0 = cmul(g0, y1); }
        }
        __syncwarp();
        uint32_t b[4][4];
#pragma unroll
        for (int k = 0; k < 4; k++) { ldsm(af[k], lda ^ (k << 5)); ldsm(b[k], (ldb ^ (k << 5)) + 2048); }
#pragma unroll
        for (int e = 0; e < 8; e += 2) {
            stsm_x4((st2 ^ (e << 4)) + e * 128, hcmul(ge[e & 3], v[2 + (e >> 2)]), hcmul(ge[0], v[4 + (e >> 1)]), hcmul(ge[(e & 3) + 1], v[2 + (e >> 2)]), hcmul(ge[2], v[4 + (e >> 1)]));
            if (!(e & 3)) stsm_x4((st3 ^ (e << 4)) + e * 128, e ? hcmul(v[0].x, v[e]) : v[0].x, hcmul(v[0].x, v[e + 1]), hcmul(v[0].x, v[e + 2]), hcmul(v[0].x, v[e + 3]));
            mma(acc[0], af[e >> 1], b[e >> 1]);
            mma(acc[1], af[e >> 1], b[e >> 1] + 2);
        }
        __syncwarp();
        if (sel == 0x1076) CSK(3);
    }
    rest();
#pragma unroll
    for (int e = 0; e < 5; e++) k2048 += __shfl_xor_sync(~0u, k2048, 1 << e);
    {
        float* Pp = reinterpret_cast<float*>(tab + warp * 256);
        auto sw = [](int i) { return i ^ ((i >> 2) & 24); };
#pragma unroll
        for (int h = 0; h < 2; h++) {
            const int b = g + 8 * h;
            *reinterpret_cast<float2*>(Pp + sw(8 * b + 2 * t)) = make_float2(acc[0][2 * h] * unscale, acc[0][2 * h + 1] * unscale);
            *reinterpret_cast<float2*>(Pp + 128 + sw(8 * b + 2 * t)) = make_float2(acc[1][2 * h] * unscale, acc[1][2 * h + 1] * unscale);
            *reinterpret_cast<float2*>(Pp + 256 + sw(4 * b + 2 * (t & 1) + 64 * (t >> 1))) = make_float2(acc[2][2 * h] * unscale, acc[2][2 * h + 1] * unscale);
            *reinterpret_cast<float2*>(Pp + 384 + sw(2 * b + 32 * t)) = make_float2(acc[3][2 * h] * unscale, acc[3][2 * h + 1] * unscale);
            Pp[512 + sw(b + 32 * t)] = acc[4][2 * h] * unscale;
            Pp[512 + sw(b + 32 * t + 16)] = acc[4][2 * h + 1] * unscale;
        }
        if (lane == 0) Pp[640] = k2048 * unscale;
    }
    CSK(4);
    asm volatile("bar.sync %0, %1;" ::"r"(grp + 4), "r"(grp < 4 ? 64 : 96) : "memory");
    if (warp == 2) return;
    const float* Kp = reinterpret_cast<const float*>(tab);
    auto ksum = [&](int i) -> float { return rbf(Kp[i] + Kp[1024 + i] + (grp < 4 ? 0.f : Kp[2048 + i])); };
    auto ksum2 = [&](int q) -> float2 {
        q ^= (q >> 2) & 12;
        const float2 a = reinterpret_cast<const float2*>(Kp)[q], b = reinterpret_cast<const float2*>(Kp)[512 + q];
        const float2 c = grp < 4 ? make_float2(0.f, 0.f) : reinterpret_cast<const float2*>(Kp)[1024 + q];
        return make_float2(a.x + b.x + c.x, a.y + b.y + c.y);
    };
    {
        uint2* W2 = reinterpret_cast<uint2*>(in.tap + d * (TAPB / 16)) + 8;
        uint2* E4 = W2 + (TAPE - 64) / 8;
        float2 v = ksum2(64 * warp + lane), z = ksum2(64 * warp + 32 + lane), y = ksum2(128 + tid);
        const int q = (96 + tid) ^ (((96 + tid) >> 2) & 6);
        const float4 ua = reinterpret_cast<const float4*>(Kp)[q], uc = reinterpret_cast<const float4*>(Kp)[256 + q], ud = grp < 4 ? make_float4(0.f, 0.f, 0.f, 0.f) : reinterpret_cast<const float4*>(Kp)[512 + q];
        const float4 ub = make_float4(uc.x + ud.x, uc.y + ud.y, uc.z + ud.z, uc.w + ud.w);
        const float s1 = ksum(tid == 31 ? 336 : lane ? 384 : 103), s2 = ksum(tid == 31 ? 512 : tid ? 640 : 231);
        if (tid == 0) v.x += __uint_as_float(kp.pdsk << 16);
        if (tid == 63) y.y -= s1;
        const uint32_t lo = pack2(v.x, v.y), hi = pack2(z.x, z.y), tp = pack2(y.x, y.y);
        uint32_t nl = __shfl_sync(~0u, lo, lane - 1), nh = __shfl_sync(~0u, lane == 31 ? lo : hi, lane - 1), nt = __shfl_sync(~0u, tp, lane + 1);
        if (lane == 0) nl = warp ? __float_as_uint(s1) : 0u;
        if (lane == 31) nt = warp ? 0u : __float_as_uint(s1) >> 16;
        W2[64 * warp + lane] = make_uint2(__byte_perm(lo, nl, 0x7610), __byte_perm(lo, 0, 0x1032));
        W2[64 * warp + lane + 32] = make_uint2(__byte_perm(hi, nh, 0x7610), __byte_perm(hi, 0, 0x1032));
        reinterpret_cast<uint4*>(W2)[64 + tid] = make_uint4(__byte_perm(tp, __float_as_uint(s2), tid ? 0x1010 : 0x7610), __byte_perm(tp, 0, 0x1010), __byte_perm(tp, 0, 0x1032), __byte_perm(nt, tp, 0x7610));
        E4[(tid < 32 ? 159 : 209 - 32) + tid] = make_uint2(pack2(ua.x + ub.x, ua.y + ub.y), pack2(ua.z + ub.z, ua.w + ub.w - (tid == 31 ? s2 : 0.f)));
        if (tid == 63) E4[241] = make_uint2(__float_as_uint(s2) >> 16, 0u);
    }
    CSK(5);
    SPAN(0, 3);
}

#define CV_SLEEP 40
#define CV_LD "ld.relaxed.gpu.global"
#define CV_NL 1
#define CV_D2 3
#define CV_PDH 12
#define CV_PDF 4
#define CV_HAND 7
constexpr int CV_CPB = 5;
constexpr int CV_THREADS = 512;
constexpr int UPADF = 128;
constexpr int ULEN = UPADF + SEQ;
constexpr int XLEN = XCP;
constexpr int BX_5 = 0, BX_3 = 3264, BX_9 = 6528, BX_7 = 8960, BX_LEN = 11392;
constexpr int CV_SM_U = 0;
constexpr int CV_SM_T = CV_CPB * ULEN * 2;
constexpr int CV_SM_B = CV_SM_T + CV_CPB * TAPB;
constexpr int CV_SM_X = CV_SM_B + CV_CPB * BX_LEN;
constexpr int CV_SM_Y = (CV_SM_X + CV_CPB * XLEN * 2 + 127) & ~127;
constexpr int CV_SM_CNT = CV_SM_Y + CV_CPB * 8192;
constexpr int CV_SM_O = CV_SM_CNT + 128;
constexpr int CV_SMEM = CV_SM_O + 20480 + CST_EXTRA;
static_assert(ULEN % 128 == 0 && CV_SM_B % 128 == 0 && CV_SM_CNT % 128 == 0, "layout");

__device__ __forceinline__ uint32_t sub2(uint32_t x, uint32_t m) {
    const __nv_bfloat162 d = __hsub2(*reinterpret_cast<const __nv_bfloat162*>(&x), *reinterpret_cast<const __nv_bfloat162*>(&m));
    return *reinterpret_cast<const uint32_t*>(&d);
}
__device__ __forceinline__ uint32_t add2(uint32_t x, uint32_t y) {
    const __nv_bfloat162 d = __hadd2_rn(*reinterpret_cast<const __nv_bfloat162*>(&x), *reinterpret_cast<const __nv_bfloat162*>(&y));
    return *reinterpret_cast<const uint32_t*>(&d);
}
__device__ __forceinline__ void wgmma_fence() { asm volatile("wgmma.fence.sync.aligned;" ::: "memory"); }
__device__ __forceinline__ void wgmma_commit() { asm volatile("wgmma.commit_group.sync.aligned;" ::: "memory"); }
template <int N> __device__ __forceinline__ void wgmma_wait() { asm volatile("wgmma.wait_group.sync.aligned %0;" ::"n"(N) : "memory"); }
__device__ __forceinline__ uint64_t make_desc(uint32_t addr, uint32_t lbo, uint32_t sbo, uint32_t mode) {
    return (uint64_t)((addr & 0x3FFFF) >> 4) | ((uint64_t)(lbo >> 4) << 16) | ((uint64_t)(sbo >> 4) << 32) | ((uint64_t)mode << 62);
}
__device__ __forceinline__ void wgmma_rs128(float (&d)[64], uint2 hi, uint2 lo, uint64_t db, int acc) {
    asm volatile("{\n.reg .pred p;\nsetp.ne.b32 p, %69, 0;\nwgmma.mma_async.sync.aligned.m64n128k16.f32.bf16.bf16 {%0,%1,%2,%3,%4,%5,%6,%7,%8,%9,%10,%11,%12,%13,%14,%15,%16,%17,%18,%19,%20,%21,%22,%23,%24,%25,%26,%27,%28,%29,%30,%31,%32,%33,%34,%35,%36,%37,%38,%39,%40,%41,%42,%43,%44,%45,%46,%47,%48,%49,%50,%51,%52,%53,%54,%55,%56,%57,%58,%59,%60,%61,%62,%63}, {%64,%65,%66,%67}, %68, p, 1, 1, 0;\n}"
                 : "+f"(d[0]), "+f"(d[1]), "+f"(d[2]), "+f"(d[3]), "+f"(d[4]), "+f"(d[5]), "+f"(d[6]), "+f"(d[7]), "+f"(d[8]), "+f"(d[9]), "+f"(d[10]), "+f"(d[11]), "+f"(d[12]), "+f"(d[13]), "+f"(d[14]), "+f"(d[15]), "+f"(d[16]), "+f"(d[17]), "+f"(d[18]), "+f"(d[19]), "+f"(d[20]), "+f"(d[21]), "+f"(d[22]), "+f"(d[23]), "+f"(d[24]), "+f"(d[25]), "+f"(d[26]), "+f"(d[27]), "+f"(d[28]), "+f"(d[29]), "+f"(d[30]), "+f"(d[31]), "+f"(d[32]), "+f"(d[33]), "+f"(d[34]), "+f"(d[35]), "+f"(d[36]), "+f"(d[37]), "+f"(d[38]), "+f"(d[39]), "+f"(d[40]), "+f"(d[41]), "+f"(d[42]), "+f"(d[43]), "+f"(d[44]), "+f"(d[45]), "+f"(d[46]), "+f"(d[47]), "+f"(d[48]), "+f"(d[49]), "+f"(d[50]), "+f"(d[51]), "+f"(d[52]), "+f"(d[53]), "+f"(d[54]), "+f"(d[55]), "+f"(d[56]), "+f"(d[57]), "+f"(d[58]), "+f"(d[59]), "+f"(d[60]), "+f"(d[61]), "+f"(d[62]), "+f"(d[63])
                 : "r"(hi.x), "r"(hi.y), "r"(lo.x), "r"(lo.y), "l"(db), "r"(acc));
}
template <int V> struct Int { __device__ constexpr operator int() const { return V; } };
__device__ __forceinline__ void sts4(uint32_t a, const uint32_t* v) { asm volatile("st.shared.v4.u32 [%0], {%1,%2,%3,%4};" ::"r"(a), "r"(v[0]), "r"(v[1]), "r"(v[2]), "r"(v[3]) : "memory"); }
__device__ __forceinline__ uint32_t lds1(uint32_t a) { uint32_t v; asm volatile("ld.shared.u32 %0, [%1];" : "=r"(v) : "r"(a) : "memory"); return v; }
__device__ __forceinline__ uint32_t lds1v(uint32_t a) { uint32_t v; asm volatile("ld.volatile.shared.u32 %0, [%1];" : "=r"(v) : "r"(a) : "memory"); return v; }
__device__ __forceinline__ uint4 lds4(uint32_t a) { uint4 v; asm volatile("ld.shared.v4.u32 {%0,%1,%2,%3}, [%4];" : "=r"(v.x), "=r"(v.y), "=r"(v.z), "=r"(v.w) : "r"(a) : "memory"); return v; }
__device__ __forceinline__ uint4 ldx(uint32_t a) {
    uint4 v;
    asm volatile("ld.shared.v2.u32 {%0,%1}, [%4];\nld.shared.v2.u32 {%2,%3}, [%4+128];" : "=r"(v.x), "=r"(v.y), "=r"(v.z), "=r"(v.w) : "r"(a) : "memory");
    return v;
}
__device__ __forceinline__ void cv_store(unsigned char* p, uint4 x, uint4 y) {
    asm volatile("st.relaxed.gpu.global.v2.u32 [%0], {%1,%2};" ::"l"(p), "r"(add2(x.x, __byte_perm(y.x, y.y, 0x5410))), "r"(add2(x.y, __byte_perm(y.z, y.w, 0x5410))) : "memory");
    asm volatile("st.relaxed.gpu.global.v2.u32 [%0], {%1,%2};" ::"l"(p + 128), "r"(add2(x.z, __byte_perm(y.x, y.y, 0x7632))), "r"(add2(x.w, __byte_perm(y.z, y.w, 0x7632))) : "memory");
}
__device__ __forceinline__ int usw(int ch) { return ch ^ ((ch >> 3) & 1); }
__global__ void __launch_bounds__(CV_THREADS, 1) conv_kernel(int layer, const uint4* __restrict__ piv, const float4* __restrict__ sum, const bf16* __restrict__ x1T,
                                                             bf16* __restrict__ dst, const uint4* __restrict__ tap, const __grid_constant__ CUtensorMap tmOut) {
    extern __shared__ __align__(1024) unsigned char sm[];
    SPAN(3 + 4 * layer, 0);
    bf16* Us = reinterpret_cast<bf16*>(sm + CV_SM_U);
    bf16* Xs = reinterpret_cast<bf16*>(sm + CV_SM_X);
#define CV_IDX int tid; asm volatile("mov.u32 %0, %tid.x;" : "=r"(tid)); const int lane = tid & 31, warp = __shfl_sync(~0u, tid >> 5, 0);
    const int d0 = blockIdx.x * CV_CPB, tile = blockIdx.x; (void)tile;
    const uint32_t cnt = smem_u32(sm + CV_SM_CNT);
    struct Lc { uint32_t a4, a8, uc, ud, y, e4, en, sp, ss; int go; };
    auto lane_consts = [&](int lane, int c) {
        const int mat = lane >> 3, r = lane & 7, g = lane >> 2, ti = lane & 3, e = g - 2 * ti;
        const int j2 = 13 + (r ^ 1) + 8 * (mat >> 1), j3 = j2 + 2, i0 = 8 * (mat & 1);
        const uint32_t sb = smem_u32(sm), oc = sb + usw(16 * (mat >> 1) + 2 * r + (mat & 1)) * 16;
        const Lc l = {sb + CV_SM_B + c * BX_LEN + ((j2 & 1) ? BX_3 + (4 * j2 + i0 + 84) * 2 : BX_5 + (4 * j2 + i0 + 80) * 2),
                      sb + CV_SM_B + c * BX_LEN + ((j3 & 1) ? BX_7 : BX_9) + (8 * j3 + i0 + 136) * 2,
                      oc + CV_SM_U + (c * ULEN + UPADF) * 2, sb + CV_SM_U + (c * ULEN + UPADF) * 2 + usw(16 * mat + 2 * r + 2) * 16, oc + CV_SM_Y + c * 8192,
                      sb + CV_SM_T + c * TAPB + TAPE + (307 + 2 * g - ti) * 4, sb + CV_SM_T + c * TAPB + (528 + e) * 4,
                      e == -5 ? 0x4410u : e == -4 ? 0x1044u : 0x4444u, e == 3 ? 0x4410u : e == 4 ? 0x1044u : 0x4444u,
                      c * XCP * 2 + (lane >> 4) * 256 + (lane & 15) * 8};
        asm volatile("st.shared.u32 [%0], %1;" ::"r"(sb + CV_SM_CNT + 120), "r"(l.y ^ l.a4 ^ l.a8 ^ l.uc ^ l.ud ^ l.e4 ^ l.en ^ l.sp ^ l.ss ^ l.go) : "memory");
        return l;
    };
    unsigned char* const dq = reinterpret_cast<unsigned char*>(dst + (size_t)d0 * XCP);
    auto far = [&](auto T0_, const auto& seq, const Lc& lc, int c, int lane, const uint2 (&f)[20], uint32_t kk) {
        constexpr int T0 = T0_, T1 = T0 + 6, TC = T0 > 7 ? T0 : 7, NS = sizeof(seq) / sizeof(seq[0]), PD = T0 > 7 ? CV_PDH : CV_PDF;
        uint32_t bq[28], yw[4], yz[4], P, S;
        uint4 xv, yv;
        asm("prmt.b32 %0, %1, 0, %2;" : "=r"(P) : "r"(kk), "r"(lc.sp));
        asm("prmt.b32 %0, %1, 0, %2;" : "=r"(S) : "r"(kk), "r"(lc.ss));
#pragma unroll
        for (int k = 0; 2 * k < T1 - TC + 4; k++) ldsm_x4(bq + 4 * k, lc.uc + (TC - 8) * 256 + 512 * k);
#pragma unroll
        for (int k = 0; 4 * k < T1 - TC; k++) ldsm_x4(bq + 20 + 4 * k, lc.ud + (TC - 8) * 256 + 1024 * k);
        CST(3);
        mbar_wait(cnt + 8 * c, 0);
        mbar_wait(cnt + 40, 0);
        CST(4);
        float acc[6][4] = {};
        uint32_t a[PD + 1][4];
#pragma unroll
        for (int i = -PD; i < NS + 3; i++) {
            if (i + PD < NS) ldsm_x4_t(a[(i + PD) % (PD + 1)], seq[i + PD] < 32 ? lc.a4 + (seq[i + PD] - 2) * 128 : lc.a8 + (seq[i + PD] - 34) * 256);
            if (i < 0) continue;
#pragma unroll
            for (int T = T0; T < T1; T++) {
                if (i >= NS) break;
                const int ee = seq[i] < 32 ? 2 * T - 6 - seq[i] : T + 35 - seq[i];
                if (i == 0 && T >= TC) mma_bf16(acc[T - T0], P, 0u, S, P, bq[2 * (T - TC)], bq[2 * (T - TC) + 1]);
                if (i == 1 && T >= TC) mma_bf16_k8(acc[T - T0], 0u, S, bq[20 + T - TC]);
                if (i == (T >= TC ? 2 : 0)) mma_bf16(acc[T - T0], f[19].x, 0u, f[19].y, f[19].x, bq[2 * (T - TC + 4)], bq[2 * (T - TC + 4) + 1]);
                if (seq[i] < 32 ? ee >= 0 && ee <= 9 : ee >= 10) mma_bf16(acc[T - T0], a[i % (PD + 1)][0], a[i % (PD + 1)][1], a[i % (PD + 1)][2], a[i % (PD + 1)][3], f[ee].x, f[ee].y);
            }
#pragma unroll
            for (int k = 0; k < 3; k++) {
                const int o = 256 * T0 + 512 * k;
                auto at = [&](int d) { return i - d >= 0 && i - d < NS && seq[i - d < 0 ? 0 : i - d < NS ? i - d : 0] == 2 * T0 + 4 * k - 4; };
                if (at(CV_D2)) {
                    cv_store(dq + lc.go + o, xv, yv);
                    if (layer > 19 - 2 * k) __trap();
                }
                if (at(-2)) { ldsm_x4_t(yw, lc.y + o); ldsm_x4_t(yz, lc.y + 3584 + o); }
                if (at(1)) {
#pragma unroll
                    for (int q = 0; q < 4; q++) yw[q] = add2(add2(yw[q], yz[q]), pack2(acc[2 * k + (q >> 1)][2 * (q & 1)], acc[2 * k + (q >> 1)][2 * (q & 1) + 1]));
                    stsm_x4_t(lc.y + o, yw[0], yw[1], yw[2], yw[3]);
                    xv = ldx(smem_u32(Xs) + lc.go + o);
                    __syncwarp();
                    yv = lds4(smem_u32(sm + CV_SM_Y) + c * 8192 + o + usw(lane) * 16);
                    if (layer > 20 - 2 * k) __trap();
                    if (k == 2) CST(6);
                }
            }
        }
    };
    TSTAMP1X(9, 256);
    if (threadIdx.x >= 256) {
        if (threadIdx.x < 288 && elect()) {
            mbar_init(cnt + 48, 1);
            asm volatile("fence.mbarrier_init.release.cluster;" ::: "memory");
            bulk_load(smem_u32(sm + CV_SM_T), tap + d0 * (TAPB / 16), CV_CPB * TAPB, cnt + 48);
            mbar_expect_tx(cnt + 48, CV_CPB * TAPB);
        }
        CV_IDX
        const int wgu = (warp >> 2) & 1, g = lane >> 2, ti = lane & 3;
        CST(1);
        if (warp > 8 && elect()) {
            if (warp < 15) mbar_init(cnt + 8 * (warp - 9), warp == 14 ? 8 : 4);
            else if (layer) prefetch_tmap(&tmOut);
        }
        if (warp < 13 && lane < 17 - (warp == 12)) {
            const int off = warp == 12 ? CV_SM_U : CV_SM_B + (warp == 11 ? BX_7 : (warp - 8) * BX_3), str = warp == 12 ? ULEN * 2 : BX_LEN;
#pragma unroll
            for (int c = 0; c < CV_CPB; c++) *reinterpret_cast<uint4*>(sm + off + c * str + 16 * lane) = make_uint4(0, 0, 0, 0);
        }
        fence_async_smem();
        asm volatile("bar.arrive 3, 512;" ::: "memory");
        asm volatile("bar.sync 1, 256;" ::: "memory");
        TSTAMP1X(10, 256);
        asm volatile("setmaxnreg.inc.sync.aligned.u32 168;");
        const uint32_t Tc = smem_u32(sm + CV_SM_T) + (16 + 128 * (warp & 2) + 8 * (warp & 1) + g - 2 * ti) * 4;
        uint2 fa[8][2], fn[8][2];
        auto near_taps = [&](uint2 (&f)[8][2], int c) {
#pragma unroll
            for (int m = 0; m < 16; m++) f[m >> 1][m & 1] = make_uint2(lds1v(Tc + c * TAPB + 64 * (m >> 1) - 32 * (m & 1)), lds1v(Tc + c * TAPB + 64 * (m >> 1) - 32 * (m & 1) + 512));
        };
        CST(6);
        mbar_wait(cnt + 48, 0);
        TSTAMP1X(11, 256); CST(5);
        near_taps(fa, 3 * wgu);
        near_taps(fn, 2 - wgu);
        const int hc = wgu ? warp & 3 : 4;
        const Lc lc = lane_consts(lane, hc);
        TSTAMP1X(12, 256); CST(0);
        uint32_t ya = smem_u32(sm + CV_SM_Y) + wgu * 8192 + (warp & 2) * 2048 + usw(2 * lane + (warp & 1)) * 16;
        uint64_t db = make_desc(smem_u32(Us + wgu * ULEN + UPADF), 16, 256, 3);
        if (wgu) asm volatile("bar.sync 6, 384;" ::: "memory");
        int c = wgu;
        auto chain = [&](const uint2 (&f)[8][2], auto&& meanwhile) {
            float acc[64];
            asm volatile("bar.sync %0, %1;" ::"r"(c ? 4 + wgu : 2), "r"(c ? 256 : 384) : "memory");
            TSTAMPC(1 + 3 * c);
            if (c < 2) CST(7);
            if (c == 0) fence_async_smem();
            wgmma_fence();
#pragma unroll
            for (int m = 0; m < 8; m++) {
                wgmma_rs128(acc, f[m][0], f[m][1], db - (uint64_t)(2 * m), m);
                if (m == CV_HAND && c < 4) asm volatile("bar.arrive %0, 256;" ::"r"(5 - wgu) : "memory");
            }
            wgmma_commit();
            asm volatile("griddepcontrol.launch_dependents;" ::: "memory");
            TSTAMPC(2 + 3 * c); CST(13 + (c >> 1));
            meanwhile();
            wgmma_wait<0>();
            TSTAMPC(3 + 3 * c); CST(10 + (c >> 1));
            uint32_t w[16];
#pragma unroll
            for (int j = 0; j < 16; j++) w[j] = j ? pack2(acc[4 * j] + acc[4 * j - 2], acc[4 * j + 1] + acc[4 * j - 1]) : pack2(acc[0], acc[1]);
#pragma unroll
            for (int j = 0; j < 16; j += 4) stsm_x4_t(ya + 256 * j, w[j], w[j + 1], w[j + 2], w[j + 3]);
            __syncwarp();
            if (lane == 0) mbar_arrive(cnt + 8 * c);
            c += 2; ya += 16384; db += ULEN / 4;
        };
        const uint32_t e4 = lc.e4, e8 = e4 + 428 - 4 * g;
        uint2 fl[4];
        uint32_t kk;
#pragma unroll 1
        for (;;) {
            if (c != 1) chain(fa, [&] {
                if (c == 3 || warp + c == 12) {
#pragma unroll
                    for (int k = 0; k < 19; k++) (k < 16 ? fn[(k >> 1) & 7][k & 1] : fl[k & 3]) = make_uint2(lds1(k < 10 ? e4 + 32 * k + 16 : e8 + 32 * k - 304), lds1(k < 10 ? e4 + 32 * k : e8 + 32 * k - 320));
                    fl[3] = make_uint2(lds1(lc.en), lds1(lc.en - 32));
                    kk = lds1(smem_u32(sm + CV_SM_T) + TAPB * hc + TAPE + 1672);
                }
            });
            if (c > 4) break;
            if (c == 2) { asm volatile("bar.sync 7, 384;" ::: "memory"); fence_async_smem(); }
            chain(fn, [&] { if (c == 2) near_taps(fa, 4); });
        }
        TSTAMP1X(6, 256); CST(2);
        if (wgu || warp == 8) {
            constexpr int seq[29] = {5, 6, 32, 7, 33, 8, 34, 9, 35, 10, 36, 11, 12, 13, 14, 15, 16, 17, 37, 18, 38, 19, 20, 21, 39, 22, 40, 23, 24};
            uint2 f[20];
#pragma unroll
            for (int k = 0; k < 20; k++) f[k] = k < 16 ? fn[(k >> 1) & 7][k & 1] : fl[k & 3];
            far(Int<10>(), seq, lc, hc, lane, f, kk);
        }
    } else {
        asm volatile("setmaxnreg.dec.sync.aligned.u32 88;");
        CV_IDX
        CST(5);
        const uint4* ppv = piv + tid;
        const float4* psv = sum + tid;
        const uint2* pxv = reinterpret_cast<const uint2*>(x1T + (size_t)d0 * XCP) + (tid >> 4) * 32 + (tid & 15);
        asm volatile("st.shared.u64 [%0], %1;" ::"r"(smem_u32(sm + CV_SM_O) + tid * 16), "l"((uint64_t)ppv ^ (uint64_t)psv ^ (uint64_t)pxv) : "memory");
        const int tc = (0x04302100 >> (4 * warp)) & 7;
        const Lc lc = lane_consts(lane, tc);
        pdl_sync();
        SPAN(3 + 4 * layer, 1);
        TSTAMP(0); CST(0);
        if (tid == 0) TSTAMPC(0);
        if (threadIdx.x == 0) { GSTAMP(g_tim, 15); }
        float4 sv[4];
        uint4 pv;
#pragma unroll
        for (int k = 0; k < 4; k++)
            asm volatile(CV_LD ".v4.f32 {%0,%1,%2,%3}, [%4];" : "=f"(sv[k].x), "=f"(sv[k].y), "=f"(sv[k].z), "=f"(sv[k].w) : "l"(psv + 256 * k) : "memory");
        asm volatile(CV_LD ".v4.u32 {%0,%1,%2,%3}, [%4];" : "=r"(pv.x), "=r"(pv.y), "=r"(pv.z), "=r"(pv.w) : "l"(ppv) : "memory");
        uint2 xe[CV_CPB], xo[CV_CPB];
#pragma unroll
        for (int c = 0; c < CV_NL; c++) {
            asm volatile(CV_LD ".v2.u32 {%0,%1}, [%2];" : "=r"(xe[c].x), "=r"(xe[c].y) : "l"(pxv + c * (XCP / 4)) : "memory");
            asm volatile(CV_LD ".v2.u32 {%0,%1}, [%2];" : "=r"(xo[c].x), "=r"(xo[c].y) : "l"(pxv + c * (XCP / 4) + 16) : "memory");
        }
#define CV_XD 300
#define CV_XW 0
        if (warp == CV_XW) {
            if (elect()) {
                const uint32_t c0 = clock();
                mbar_init(cnt + 56, 1);
                asm volatile("fence.mbarrier_init.release.cluster;" ::: "memory");
                mbar_expect_tx(cnt + 56, CV_CPB * 4096);
                while (clock() - c0 < CV_XD) ;
#pragma unroll
                for (int c = CV_NL; c < CV_CPB + CV_NL; c++) bulk_load(smem_u32(Xs + (c % CV_CPB) * XLEN), x1T + (size_t)(d0 + c % CV_CPB) * XCP, 4096, cnt + 56);
            }
            __syncwarp();
            CST(15);
        }
        uint32_t mw[4];
        float rs[8];
#pragma unroll
        for (int k = 0; k < 4; k++) {
            const uint32_t pw = k == 0 ? pv.x : k == 1 ? pv.y : k == 2 ? pv.z : pv.w;
            uint32_t vr;
            mw[k] = pack2(sv[k].x + __uint_as_float(pw << 16), sv[k].z + __uint_as_float(pw & 0xffff0000u));
            asm("cvt.rn.relu.bf16x2.f32 %0, %1, %2;" : "=r"(vr) : "f"(fmaf(-sv[k].z, sv[k].z, sv[k].w)), "f"(fmaf(-sv[k].x, sv[k].x, sv[k].y)));
            const uint32_t ve = pack2(__uint_as_float(vr << 16) + 1e-5f, __uint_as_float(vr & 0xffff0000u) + 1e-5f);
            const uint32_t sd = pack2(sqrt_apx(__uint_as_float(ve << 16)), sqrt_apx(__uint_as_float(ve & 0xffff0000u)));
            rs[2 * k] = rcp_apx(__uint_as_float(sd << 16)); rs[2 * k + 1] = rcp_apx(__uint_as_float(sd & 0xffff0000u));
        }
        if (rs[0] != 123.f) TSTAMP(13);
        const uint32_t ua = smem_u32(Us) + usw(tid + UPADF / 8) * 16;
        uint32_t uw[CV_CPB][4];
#pragma unroll
        for (int c = 0; c < CV_CPB; c++) {
            if (c == CV_NL) {
                if (warp == CV_XW) { mbar_wait(cnt + 56, 0); CST(7); }
                asm volatile("bar.sync 10, 256;" ::: "memory");
            }
            if (c == 1 || c == 2) {
#pragma unroll
                for (int k = c; k < (c == 1 ? 2 : CV_CPB); k++) {
 const uint4 v = ldx(smem_u32(Xs + k * XLEN) + (tid >> 4) * 256 + (tid & 15) * 8); xe[k] = make_uint2(v.x, v.y); xo[k] = make_uint2(v.z, v.w); }
            }
            const uint32_t e0 = sub2(xe[c].x, mw[0]), e1 = sub2(xe[c].y, mw[1]), o0 = sub2(xo[c].x, mw[2]), o1 = sub2(xo[c].y, mw[3]);
            uw[c][0] = pack2(__uint_as_float(e0 << 16) * rs[0], __uint_as_float(o0 << 16) * rs[4]); uw[c][1] = pack2(__uint_as_float(e0 & 0xffff0000u) * rs[1], __uint_as_float(o0 & 0xffff0000u) * rs[5]);
            uw[c][2] = pack2(__uint_as_float(e1 << 16) * rs[2], __uint_as_float(o1 << 16) * rs[6]); uw[c][3] = pack2(__uint_as_float(e1 & 0xffff0000u) * rs[3], __uint_as_float(o1 & 0xffff0000u) * rs[7]);
            asm volatile("st.shared.v4.u32 [%0], {%1,%2,%3,%4};" ::"r"(ua + c * ULEN * 2), "r"(uw[c][0]), "r"(uw[c][1]), "r"(uw[c][2]), "r"(uw[c][3]) : "memory");
            if (c < 2) {
                if (c == 1) fence_async_smem();
                asm volatile("bar.arrive %0, 384;" ::"r"(2 + 4 * c) : "memory");
                if (layer > 29 - c) __trap();
                CST(11 + c);
            }
        }
        asm volatile("bar.arrive 7, 384;" ::: "memory");
        asm volatile("bar.sync 3, 512;" ::: "memory");
        TSTAMP(1); CST(1);
        {
            auto box = [&](auto c0, auto c1, int chunk, int cb, bool full) {
                const uint32_t ea = smem_u32(Us + cb * ULEN) + usw(chunk + UPADF / 8 + (lane ? 1 : -1)) * 16, bx = smem_u32(sm + CV_SM_B + cb * BX_LEN) + chunk * 16;
                uint32_t lo[CV_CPB][4], hi[CV_CPB][2];
#pragma unroll
                for (int c = c0; c < c1; c++) {
                    lo[c][0] = 0;
#pragma unroll
                    for (int k = 1; k < 4; k++) lo[c][k] = __shfl_up_sync(~0u, uw[c][k], 1);
#pragma unroll
                    for (int k = 0; k < 2; k++) hi[c][k] = __shfl_down_sync(~0u, uw[c][k], 1);
                }
#pragma unroll
                for (int c = c0; c < c1; c++)
                    asm volatile("{\n.reg .pred p, q;\nsetp.eq.s32 p, %7, 0;\nsetp.eq.s32 q, %7, 31;\n@p ld.shared.v4.u32 {%0,%1,%2,%3}, [%6];\n@q ld.shared.v2.u32 {%4,%5}, [%6];\n}"
                                 : "+r"(lo[c][0]), "+r"(lo[c][1]), "+r"(lo[c][2]), "+r"(lo[c][3]), "+r"(hi[c][0]), "+r"(hi[c][1]) : "r"(ea + c * ULEN * 2), "r"(lane) : "memory");
#pragma unroll
                for (int c = c0; c < c1; c++) {
                    const uint32_t e[9] = {lo[c][1], lo[c][2], lo[c][3], uw[c][0], uw[c][1], uw[c][2], uw[c][3], hi[c][0], hi[c][1]};
                    uint32_t o[8], p[8], t[7], b3[5], b5[7];
#pragma unroll
                    for (int i = 0; i < 8; i++) { o[i] = __byte_perm(e[i], e[i + 1], 0x5432); p[i] = add2(e[i], o[i]); }
#pragma unroll
                    for (int i = 0; i < 5; i++) b3[i] = add2(o[i], p[i + 1]);
                    sts4(bx + c * BX_LEN + BX_3 + 160, b3);
#pragma unroll
                    for (int i = 1; i < 7; i++) { t[i] = add2(p[i], p[i + 1]); b5[i] = add2(t[i], e[i + 2]); }
                    sts4(bx + c * BX_LEN + BX_5 + 160, b5 + 2);
                    if (full) {
#pragma unroll
                        for (int i = 1; i < 5; i++) { b3[i] = add2(b3[i], t[i + 2]); t[i] = add2(t[i], b5[i + 2]); }
                        sts4(bx + c * BX_LEN + BX_7 + 272, b3 + 1);
                        sts4(bx + c * BX_LEN + BX_9 + 272, t + 1);
                    }
                }
            };
            auto reload = [&](int c, uint32_t a) { const uint4 v = lds4(a); uw[c][0] = v.x; uw[c][1] = v.y; uw[c][2] = v.z; uw[c][3] = v.w; };
            if (warp >= 6) {
#pragma unroll
                for (int c = 0; c < 3; c++) reload(c, ua - 1024 + (c + 2) * ULEN * 2);
            }
            if (warp >= 4) {
#pragma unroll
                for (int c = 3; c < 5; c++) reload(c, ua - 2048 + c * ULEN * 2);
            }
            box(Int<0>(), Int<3>(), warp < 6 ? tid : tid - 64, warp < 6 ? 0 : 2, warp < 4);
            if (warp >= 4) box(Int<3>(), Int<5>(), tid - 128, 0, true);
            else if (tid >= 128 - CV_CPB) {
                const int c = 127 - tid;
                const uint2 v = *reinterpret_cast<const uint2*>(Us + c * ULEN + UPADF);
                const float s1 = __uint_as_float(v.x << 16), s2 = s1 + __uint_as_float(v.x & 0xffff0000u), s3 = s2 + __uint_as_float(v.y << 16), s4 = s3 + __uint_as_float(v.y & 0xffff0000u);
                unsigned char* bc = sm + CV_SM_B + c * BX_LEN;
                *reinterpret_cast<uint32_t*>(bc + BX_5 + 156) = pack2(s1, s2);
                *reinterpret_cast<uint2*>(bc + BX_7 + 264) = make_uint2(v.x << 16, pack2(s2, s3));
                *reinterpret_cast<uint2*>(bc + BX_9 + 264) = make_uint2(pack2(s1, s2), pack2(s3, s4));
            }
        }
        __syncwarp();
        if (lane == 0) mbar_arrive(cnt + 40);
        TSTAMP(2); CST(2);
        if (layer && blockIdx.x == 0 && tid == 224) g_epoch = ld_epoch();
        __syncwarp();
        if ((0x6e >> warp) & 1) {
            constexpr int seq[16] = {0, 1, 2, 3, 4, 5, 6, 32, 7, 8, 9, 33, 10, 34, 11, 12};
            uint2 f[20];
            mbar_wait(cnt, 0);
            const uint32_t e8 = lc.e4 + 428 - (lane & 28);
#pragma unroll
            for (int k = 0; k < 13; k++) f[k] = make_uint2(lds1(k < 10 ? lc.e4 + 32 * k + 16 : e8 + 32 * k - 304), lds1(k < 10 ? lc.e4 + 32 * k : e8 + 32 * k - 320));
            f[19] = make_uint2(lds1(lc.en), lds1(lc.en - 32));
            far(Int<4>(), seq, lc, tc, lane, f, lds1(smem_u32(sm + CV_SM_T) + TAPB * tc + TAPE + 1672));
        }
    }
    {
        CV_IDX
        if ((0xc91 >> warp) & 1) {
            const int c = __popc(0xc91 & ((1 << warp) - 1));
            uint4 xv[2], yv[2];
#pragma unroll
            for (int k = 0; k < 2; k++) xv[k] = ldx(smem_u32(Xs + c * XLEN) + 512 * k + (lane >> 4) * 256 + (lane & 15) * 8);
            const uint32_t u0 = lds1(smem_u32(Us + c * ULEN) + (lane == 31 ? UPADF * 2 : 0));
            mbar_wait(cnt + 8 * c, 0);
#pragma unroll
            for (int k = 0; k < 2; k++) yv[k] = lds4(smem_u32(sm + CV_SM_Y) + c * 8192 + 512 * k + usw(lane) * 16);
            const uint4 yz = lds4(smem_u32(sm + CV_SM_Y) + c * 8192 + 4096 + usw(lane) * 16);
            const float kk = __uint_as_float(lds1(smem_u32(sm + CV_SM_T) + TAPB * c + TAPE + 1272) << 16);
            yv[1].x = add2(yv[1].x, yz.x); yv[1].y = add2(yv[1].y, yz.y); yv[1].z = add2(yv[1].z, yz.z);
            yv[1].w = pack2(fmaf(kk, __uint_as_float(u0 << 16), __uint_as_float(yv[1].w << 16) + __uint_as_float(yz.w << 16)),
                            fmaf(kk, __uint_as_float(u0 << 16) + __uint_as_float(u0 & 0xffff0000u), __uint_as_float(yv[1].w & 0xffff0000u) + __uint_as_float(yz.w & 0xffff0000u)));
#pragma unroll
            for (int k = 0; k < 2; k++) cv_store(dq + c * XCP * 2 + (lane >> 4) * 256 + (lane & 15) * 8 + 512 * k, xv[k], yv[k]);
        }
        TSTAMP(4); CST(8);
        if (layer == 1) {
            const int rb = (blockIdx.x >> 3) + (warp & 8) * 2, cg = blockIdx.x & 7, ch = (tid >> 3) & 31;
            const bf16* src = dst + (size_t)(cg * 80 + ch) * XCP + rb * 64 + (tid & 7) * 8;
            uint32_t v[3][4];
            __syncthreads();
            if (warp & 8) { const uint32_t c0 = clock(); while (clock() - c0 < 300) ; }
            uint32_t todo = (warp & 4) ? 3 : 7;
#pragma unroll 1
            for (int it = 0; it < SPIN_MAX; it++) {
#pragma unroll
                for (int k = 0; k < 3; k++)
                    if (todo >> k & 1)
                        asm volatile("ld.relaxed.gpu.global.v4.u32 {%0,%1,%2,%3}, [%4];" : "=r"(v[k][0]), "=r"(v[k][1]), "=r"(v[k][2]), "=r"(v[k][3]) : "l"(src + k * (32 * XCP)) : "memory");
#pragma unroll
                for (int k = 0; k < 3; k++)
                    if ((todo >> k & 1) && v[k][0] != ~0u && v[k][1] != ~0u && v[k][2] != ~0u && v[k][3] != ~0u) {
                        *reinterpret_cast<uint4*>(sm + (32 * k + ch) * 272 + ((tid & 7) + (warp & 8)) * 16) = make_uint4(v[k][0], v[k][1], v[k][2], v[k][3]);
                        todo ^= 1u << k;
                    }
                if (!todo) break;
                __nanosleep(CV_SLEEP);
            }
            __syncwarp();
            asm volatile("bar.sync %0, 256;" ::"r"(8 + (warp >> 3)) : "memory");
            uint32_t w[12];
#pragma unroll
            for (int k = 0; k < 3; k++) ldsm_x4(&w[4 * k], smem_u32(sm) + min(32 * k + lane, 79) * 272 + warp * 16);
            const uint32_t ot = smem_u32(sm + CV_SM_O) + warp * 1280, oa = ot + (lane & 7) * 160 + (lane >> 3) * 16;
            stsm_x4_t(oa, w[0], w[1], w[2], w[3]);
            stsm_x4_t(oa + 64, w[4], w[5], w[6], w[7]);
            asm volatile("stmatrix.sync.aligned.m8n8.x2.trans.shared.b16 [%0], {%1,%2};" ::"r"(oa + 128), "r"(w[8]), "r"(w[9]) : "memory");
            fence_async_smem();
            __syncwarp();
            if (lane == 0) {
                asm volatile("cp.async.bulk.tensor.3d.global.shared::cta.bulk_group [%0, {%1, %2, %3}], [%4];" ::"l"(&tmOut), "r"(cg * 80), "r"((rb >> 1) * 64 + 8 * (warp & 7)), "r"(rb & 1), "r"(ot) : "memory");
                asm volatile("cp.async.bulk.commit_group;" ::: "memory");
                asm volatile("cp.async.bulk.wait_group.read 0;" ::: "memory");
            }
        }
    }
    TSTAMP(3); CST(9); CST_END;
    GSTAMP(g_tim, 14);
    SPAN(3 + 4 * layer, 3);
}

template <int TA, int TB>
__device__ __forceinline__ void wgmma_n240(float (&d)[120], uint64_t da, uint64_t db, int acc) {
    asm volatile("{\n.reg .pred p;\nsetp.ne.b32 p, %124, 0;\nwgmma.mma_async.sync.aligned.m64n240k16.f32.bf16.bf16 {%0,%1,%2,%3,%4,%5,%6,%7,%8,%9,%10,%11,%12,%13,%14,%15,%16,%17,%18,%19,%20,%21,%22,%23,%24,%25,%26,%27,%28,%29,%30,%31,%32,%33,%34,%35,%36,%37,%38,%39,%40,%41,%42,%43,%44,%45,%46,%47,%48,%49,%50,%51,%52,%53,%54,%55,%56,%57,%58,%59,%60,%61,%62,%63,%64,%65,%66,%67,%68,%69,%70,%71,%72,%73,%74,%75,%76,%77,%78,%79,%80,%81,%82,%83,%84,%85,%86,%87,%88,%89,%90,%91,%92,%93,%94,%95,%96,%97,%98,%99,%100,%101,%102,%103,%104,%105,%106,%107,%108,%109,%110,%111,%112,%113,%114,%115,%116,%117,%118,%119}, %120, %121, p, 1, 1, %122, %123;\n}"
                 : "+f"(d[0]), "+f"(d[1]), "+f"(d[2]), "+f"(d[3]), "+f"(d[4]), "+f"(d[5]), "+f"(d[6]), "+f"(d[7]), "+f"(d[8]), "+f"(d[9]), "+f"(d[10]), "+f"(d[11]), "+f"(d[12]), "+f"(d[13]), "+f"(d[14]), "+f"(d[15]), "+f"(d[16]), "+f"(d[17]), "+f"(d[18]), "+f"(d[19]), "+f"(d[20]), "+f"(d[21]), "+f"(d[22]), "+f"(d[23]), "+f"(d[24]), "+f"(d[25]), "+f"(d[26]), "+f"(d[27]), "+f"(d[28]), "+f"(d[29]), "+f"(d[30]), "+f"(d[31]), "+f"(d[32]), "+f"(d[33]), "+f"(d[34]), "+f"(d[35]), "+f"(d[36]), "+f"(d[37]), "+f"(d[38]), "+f"(d[39]), "+f"(d[40]), "+f"(d[41]), "+f"(d[42]), "+f"(d[43]), "+f"(d[44]), "+f"(d[45]), "+f"(d[46]), "+f"(d[47]), "+f"(d[48]), "+f"(d[49]), "+f"(d[50]), "+f"(d[51]), "+f"(d[52]), "+f"(d[53]), "+f"(d[54]), "+f"(d[55]), "+f"(d[56]), "+f"(d[57]), "+f"(d[58]), "+f"(d[59]), "+f"(d[60]), "+f"(d[61]), "+f"(d[62]), "+f"(d[63]), "+f"(d[64]), "+f"(d[65]), "+f"(d[66]), "+f"(d[67]), "+f"(d[68]), "+f"(d[69]), "+f"(d[70]), "+f"(d[71]), "+f"(d[72]), "+f"(d[73]), "+f"(d[74]), "+f"(d[75]), "+f"(d[76]), "+f"(d[77]), "+f"(d[78]), "+f"(d[79]), "+f"(d[80]), "+f"(d[81]), "+f"(d[82]), "+f"(d[83]), "+f"(d[84]), "+f"(d[85]), "+f"(d[86]), "+f"(d[87]), "+f"(d[88]), "+f"(d[89]), "+f"(d[90]), "+f"(d[91]), "+f"(d[92]), "+f"(d[93]), "+f"(d[94]), "+f"(d[95]), "+f"(d[96]), "+f"(d[97]), "+f"(d[98]), "+f"(d[99]), "+f"(d[100]), "+f"(d[101]), "+f"(d[102]), "+f"(d[103]), "+f"(d[104]), "+f"(d[105]), "+f"(d[106]), "+f"(d[107]), "+f"(d[108]), "+f"(d[109]), "+f"(d[110]), "+f"(d[111]), "+f"(d[112]), "+f"(d[113]), "+f"(d[114]), "+f"(d[115]), "+f"(d[116]), "+f"(d[117]), "+f"(d[118]), "+f"(d[119])
                 : "l"(da), "l"(db), "n"(TA), "n"(TB), "r"(acc));
}

__device__ __forceinline__ void wgmma_n80(float (&d)[40], uint64_t da, uint64_t db, int acc) {
    asm volatile("{\n.reg .pred p;\nsetp.ne.b32 p, %42, 0;\nwgmma.mma_async.sync.aligned.m64n80k16.f32.bf16.bf16 {%0,%1,%2,%3,%4,%5,%6,%7,%8,%9,%10,%11,%12,%13,%14,%15,%16,%17,%18,%19,%20,%21,%22,%23,%24,%25,%26,%27,%28,%29,%30,%31,%32,%33,%34,%35,%36,%37,%38,%39}, %40, %41, p, 1, 1, 0, 1;\n}"
                 : "+f"(d[0]), "+f"(d[1]), "+f"(d[2]), "+f"(d[3]), "+f"(d[4]), "+f"(d[5]), "+f"(d[6]), "+f"(d[7]), "+f"(d[8]), "+f"(d[9]), "+f"(d[10]), "+f"(d[11]), "+f"(d[12]), "+f"(d[13]), "+f"(d[14]), "+f"(d[15]), "+f"(d[16]), "+f"(d[17]), "+f"(d[18]), "+f"(d[19]), "+f"(d[20]), "+f"(d[21]), "+f"(d[22]), "+f"(d[23]), "+f"(d[24]), "+f"(d[25]), "+f"(d[26]), "+f"(d[27]), "+f"(d[28]), "+f"(d[29]), "+f"(d[30]), "+f"(d[31]), "+f"(d[32]), "+f"(d[33]), "+f"(d[34]), "+f"(d[35]), "+f"(d[36]), "+f"(d[37]), "+f"(d[38]), "+f"(d[39])
                 : "l"(da), "l"(db), "r"(acc));
}

constexpr int A1_THREADS = 384;
constexpr int A1_NST = 4;
#define A1_SKEW 8
constexpr int A1_STAGE = 16384 + WQ_STAGE;
constexpr int A1_KVP = 336;
constexpr int A1_SM_KV = 2 * A1_STAGE;
constexpr int A1_SM_END = A1_NST * A1_STAGE;
constexpr int A1_SM_BAR = A1_SM_END + 3072 + 3 * WOB + 64;
constexpr int A1_SM_RS = A1_SM_END + 512;
constexpr int A1_SM_W0 = A1_SM_END + 3072, A1_SM_W3 = A1_SM_END - 3 * WOB, A1_SM_A1 = 2 * WOB, A1_SM_A0 = A1_SM_A1 + 61440;
constexpr int A1_SM_XA = A1_SM_W0 + 2 * WOB, A1_SM_XB = A1_SM_XA + 2048;
constexpr int A1_SMEM = A1_SM_BAR + 512 + 7 * CST_EXTRA / 4;
static_assert(A1_SM_W3 >= A1_SM_KV + 144 * A1_KVP && A1_SM_W3 % 512 == 0 && A1_SM_A1 % 1024 == 0 && A1_SM_A0 <= A1_SM_KV && A1_SM_A0 + 61440 <= A1_SM_W3 && A1_SMEM <= 232448 && 11 * 4096 <= A1_STAGE, "layout");
__device__ __forceinline__ constexpr uint32_t wo_off(int h) { return h * WOB + (h < 3 ? A1_SM_W0 : h < 6 ? A1_SM_W3 - 3 * WOB : -6 * WOB); }
#define A1_FRED "red.relaxed.gpu.global.add.u32"
#define A1_FLD "ld.relaxed.gpu.global.u32"
#define ST_SLEEP 20
#define ST_SLEEP0 300
#define A1_P0 2
#define A1_PW (kb - 2)
#define A1_FSPIN SPIN_MAX
#define A1_FSLEEP 40
#define YT_LAYER 1
#define WOT 11
#define A1_WOAT 6

template <int L>
__device__ __forceinline__ void a1_mainloop(float (&acc)[120], uint32_t sbase, uint32_t bars, int wg, int tile) {
    constexpr int layer = L; (void)layer;
    const uint64_t da0 = L ? make_desc(sbase + wg * 8192, 8192, 1024, 1) : make_desc(sbase + wg * 8192, 16, 1024, 1), db0 = make_desc(sbase + 16384, 1024, 256, 3);
#pragma unroll 1
    for (int t = 0;; t++) {
        const int st = t % A1_NST;
        mbar_wait(bars + 8 * st, (t / A1_NST) & 1);
        if (t == A1_SKEW && wg == 0) mbar_wait(bars + 160, 0);
        TSTAMP3(1 + t);
        if (t == 0) CSA(0);
        wgmma_fence();
#pragma unroll
        for (int kk = 0; kk < 4; kk++) wgmma_n240<L, 1>(acc, da0 + (uint32_t)(st * (A1_STAGE / 16) + kk * (L ? 128 : 2)), db0 + (uint32_t)(st * (A1_STAGE / 16) + (kk >> 1) * (WQ_STAGE / 32) + (kk & 1) * 32), kk ? 1 : t);
        wgmma_commit();
        if (t == 9) break;
        if (t == A1_SKEW - 1 && wg == 0) wgmma_wait<0>(); else wgmma_wait<1>();
        if (t > 0 && (threadIdx.x & 127) == 0) {
            if (t != A1_SKEW || wg) mbar_arrive(bars + 8 * (A1_NST + (t - 1) % A1_NST));
            if (t == A1_SKEW - 1 && wg == 0) mbar_arrive(bars + 8 * (A1_NST + t % A1_NST));
        }
    }
}

template <bool MAP>
__global__ void __launch_bounds__(A1_THREADS, 1) a1_kernel(const __grid_constant__ Par in, const __grid_constant__ CUtensorMap tmX, const __grid_constant__ CUtensorMap tmR,
                                                           const __grid_constant__ CUtensorMap tmX1, const __grid_constant__ KgMaps tmW, const __grid_constant__ TileTab tab) {
#define layer in.layer
    const unsigned char* const wo = reinterpret_cast<const unsigned char*>(in.wop);
    float2* const rsum = reinterpret_cast<float2*>(in.sum);
    uint4* const of = in.of;
    extern __shared__ __align__(1024) unsigned char stg[];
    const uint32_t sbase = smem_u32(stg);
    const uint32_t bars = sbase + A1_SM_BAR;
    const uint32_t bar_stat = bars + 64, bar_kv = bars + 72, bar_rd = bars + 168;
    const uint32_t bar_wo = bars + 208, bar_done = bars + 216, bar_pv = bars + 224, bar_kvf = bars + 232, bar_f2 = bars + 248, bar_e2 = bars + 384, que = bars + 448;
    const int tid = threadIdx.x;
    CSK(0);
    const int w = __shfl_sync(~0u, tid >> 5, 0), wg = w >> 2;
    uint32_t smid;
    asm volatile("mov.u32 %0, %smid;" : "=r"(smid));
    const uint4 tv = tab.e[(MAP ? smid : blockIdx.x) + (tid & (smid >> 12))];
    const uint64_t pa = reinterpret_cast<const uint64_t*>(&in)[tid & (smid >> 12)], pb = reinterpret_cast<const uint64_t*>(&in)[6 + (tid & (smid >> 12))];
    const bool one = elect();
    uint32_t tz;
    const unsigned char* wq;
    auto entry = [&] { tz = __shfl_sync(~0u, tv.z, 0); wq = (const unsigned char*)(((uint64_t)__shfl_sync(~0u, tv.y, 0) << 32) | __shfl_sync(~0u, tv.x, 0)); };
    auto issue_w = [&](unsigned it) { bulk_load(sbase + (it % A1_NST) * A1_STAGE + 16384, wq + it * WQ_STAGE, WQ_STAGE, bars + 8 * (it % A1_NST)); };
    auto issue_x = [&](unsigned it, int kb) {
        asm volatile("cp.async.bulk.tensor.5d.shared::cluster.global.mbarrier::complete_tx::bytes [%0], [%1, {%3, %3, %3, %4, %5}], [%2];"
                     ::"r"(sbase + (it % A1_NST) * A1_STAGE), "l"(&tmX), "r"(bars + 8 * (it % A1_NST)), "r"(0), "r"(tz & 15), "r"(kb) : "memory");
    };
    auto first_x = [&] {
        issue_x(0, (tz >> 16) & 7); issue_x(1, ((tz >> 16) & 7) + 1);
    };
    auto expect = [&] {
#pragma unroll
        for (int i = 0; i < A1_NST; i++) mbar_expect_tx(bars + 8 * i, A1_STAGE);
    };
    if (w == 8) {
        if (one) {
            prefetch_tmap(&tmX); prefetch_tmap(&tmW.q);
#pragma unroll
            for (int i = 0; i < A1_NST; i++) mbar_init(bars + 8 * i, 1);
            asm volatile("fence.mbarrier_init.release.cluster;" ::: "memory");
        }
        __syncwarp();
        asm volatile("bar.arrive 0, 384;" ::: "memory");
        if (smid >> 12) __trap();
        entry();
        if ((tz & 0x80000010u) == 16) {
            if (one) {
                issue_w(0);
                asm volatile("griddepcontrol.wait;" ::: "memory");
                first_x();
                issue_w(1);
                expect();
                asm volatile("griddepcontrol.launch_dependents;" ::: "memory");
            }
#pragma unroll
            for (int kb = 2; kb < A1_NST; kb++) {
                __syncwarp();
                mbar_wait(bars + 8 * (kb - 2), 0);
                if (one) { issue_x(kb, ((tz >> 16) & 7) + kb); issue_w(kb); }
                CSK(6 + kb);
            }
        }
        __syncwarp();
        if (!(tz & 16) && blockIdx.x < 128) kgen_first(in, tmW, sbase + A1_SM_W0, bars - 24, one);
        __syncwarp();
    }
    if (w > 8) CSK(8);
    const bool gen = w != 8 && in.logA && blockIdx.x < 128;
    KgPar kp;
    const int w11 = w < 8 ? 2 * (w & 3) + (w >> 2) : w - 1;
    if (gen) kgen_load(in, reinterpret_cast<const bf16*>(pa), w11, kp);
    if (w > 8) CSK(9);
    if (w == 8) {
        const int tile = tz >> 24, mb = tz & 15, hg = (tz >> 8) & 7, kb0 = (tz >> 16) & 7;
        const unsigned l1 = (tz >> 4) & 1;
        if (__builtin_expect(!l1, 0)) {
            CSK(1);
            const uint32_t ep = ld_epoch();
            if (one) {
                kgen_side(in, sbase + A1_SM_W0, bars - 24);
                if (tile < 128) { first_x(); expect(); }
                asm volatile("cp.async.bulk.wait_group 0;" ::: "memory");
            }
            __syncwarp();
            asm volatile("bar.arrive 10, 96;" ::: "memory");
            CSK(6);
            if (tile < 128) {
                await_all(96 + 32 * hg, ep * 15);
                if (one) issue_w(0);
                __syncwarp();
                mbar_wait(bars, 0);
                if (one) { issue_w(1); issue_x(2, kb0 + 2); issue_w(2); }
            }
            CSK(7);
            asm volatile("bar.sync 3, 384;" ::: "memory");
            if (tile < 128 && one) {
                fence_async_smem();
                issue_x(3, kb0 + 3); issue_w(3);
                mbar_expect_tx(bars + 240, 20480);
                bulk_load(sbase + A1_SM_W0, in.x + (size_t)(mb * 128 + hg * 16) * DM, 20480, bars + 240);
            }
            __syncwarp();
            CSK(9);
        } else asm volatile("bar.sync 3, 64;" ::: "memory");
        if (tile < 128 && elect()) {
#pragma unroll 1
            for (unsigned kb = A1_NST; kb < 10; kb++) {
                mbar_wait(bars + 8 * (A1_NST + kb % A1_NST), ((kb / A1_NST) - 1) & 1);
                if (l1 && kb < 9) mbar_wait(bar_rd + 8 * (kb - A1_NST), 0);
                mbar_expect_tx(bars + 8 * (kb % A1_NST), A1_STAGE);
                issue_x(kb, kb < 5 ? kb + kb0 : kb - kb0); issue_w(kb);
                if (kb == (l1 ? A1_WOAT : 9)) {
                    if (!l1) { mbar_wait(bar_stat, 0); asm volatile("fence.proxy.async.global;" ::: "memory"); }
                    mbar_expect_tx(bar_wo, 8 * WOB);
                    bulk_load(sbase + A1_SM_W0, wo + hg * 8 * WOB, 2 * WOB, bar_wo);
                }
            }
            mbar_wait(bars + 8 * (A1_NST + 3), 1);
            bulk_load(sbase + A1_SM_W3, wo + (hg * 8 + 3) * WOB, 3 * WOB, bar_wo);
        }
        CSA(4); CSA_END;
        return;
    }
    {
        if (w < 8 && one) {
#pragma unroll 1
            for (uint32_t c = (w & 4 ? w & 2 ? 0x1111112'01111111ull : 0x1111111'01111184ull : w & 2 ? 0x3122222'01111111ull : 0x1111132'02220000ull) >> (32 * (w & 1)), b = bars + 56 * w; c; c >>= 4, b += 8)
                if (c & 15) mbar_init(b, c & 15);
            asm volatile("fence.mbarrier_init.release.cluster;" ::: "memory");
        }
        __syncwarp();
        asm volatile("bar.sync 0, 384;" ::: "memory");
        if (layer) {
            if (w == 9) asm volatile("bar.arrive 3, 64;" ::: "memory");
        } else {
            if (gen) { SPAN(0, 0); SPAN(0, 1); kgen_tables(in, reinterpret_cast<uint4*>(stg + 3 * A1_STAGE), w11, kp); }
            else if (w != 11 && w11 > 1) asm volatile("bar.arrive 9, 352;" ::: "memory");
            __syncwarp();
            if (w11 < 2) {
                asm volatile("bar.sync 10, 96;" ::: "memory");
                kgen_sums(in, sbase + A1_SM_W0, w11);
                __syncwarp();
                asm volatile("bar.arrive 9, 352;" ::: "memory");
                CSK(1);
            }
            if (w == 9) asm volatile("bar.sync 3, 384;" ::: "memory"); else asm volatile("bar.arrive 3, 384;" ::: "memory");
        }
    }
    tz = __shfl_sync(~0u, tv.z + (uint32_t)(pb >> 32), 0);
    const int tile = tz >> 24, mb = tz & 15, hg = (tz >> 8) & 7;
    float2* rst = reinterpret_cast<float2*>(stg + A1_SM_RS) + 8;
    if (wg == 2) {
        if (w == 11 && layer == 0) {
            asm volatile("bar.sync 9, 352;" ::: "memory");
            CSK(5);
            if (one) publish(64);
            __syncwarp();
            CSK(6);
        }
        if (tile >= 128) { sm_idle(layer); return; }
        if (w == 10) {
            if (one) { prefetch_tmap(&tmR); prefetch_tmap(&tmX1); }
            uint32_t ns;
            asm volatile("mov.u32 %0, %nsmid;" : "=r"(ns));
            if (MAP && ns != 132) __trap();
        }
        __syncwarp();
        if (w == 9) {
            if (layer && one) {
                mbar_expect_tx(bar_stat, 3840);
                bulk_load(sbase + A1_SM_XB, g_xb + tile * 240, 3840, bar_stat);
            }
            __syncwarp();
            uint4* pre = of + (mb * 8 + hg) * 1280 + (tid - 288);
#pragma unroll 1
            for (int k = 0; k < 5 + 5 * layer; k++) {
#pragma unroll
                for (int i = 0; i < 8; i++) asm volatile("st.global.v4.u32 [%0], {%1,%1,%1,%1};" ::"l"(pre + 32 * i), "r"(~0u) : "memory");
                pre += k < 5 ? 256 : XCP / 8;
                if (k == 4) {
                    CSA(2);
                    asm volatile("fence.acq_rel.gpu;" ::: "memory");
                    asm volatile("fence.proxy.async.global;" ::: "memory");
                    __syncwarp();
                    if (tid == 288) mbar_arrive(bar_done);
                    CSA(3);
                    pre = reinterpret_cast<uint4*>(g_yT) + tile * (5 * XCP / 8) + (tid - 288);
                }
            }
            if (layer == 0) {
                asm volatile("griddepcontrol.launch_dependents;" ::: "memory");
                await_all(64, ld_epoch() * gridDim.x);
                CSA(5);
                float4 a[2] = {};
#pragma unroll
                for (int k = 0; k < 10; k++)
#pragma unroll
                    for (int h = 0; h < 2; h++) {
                        const int c4 = min(tid - 288 + 32 * h, 59);
                        const float4 v = __ldcg(reinterpret_cast<const float4*>(g_csp + (k / 5) * 9600 + (k % 5) * 640 + hg * 80) + c4 + (c4 / 20) * 780);
                        a[h].x += v.x; a[h].y += v.y; a[h].z += v.z; a[h].w += v.w;
                    }
#pragma unroll
                for (int h = 0; h < 2; h++)
#pragma unroll
                    for (int k = 0; k < 4; k++) {
                        const float c = 0.5f * (k == 0 ? a[h].x : k == 1 ? a[h].y : k == 2 ? a[h].z : a[h].w), c1 = c - rbf(c), c2 = c1 - rbf(c1);
                        *reinterpret_cast<uint4*>(stg + A1_SM_XB + (4 * min(tid - 288 + 32 * h, 59) + k) * 16) = make_uint4(pack2(c, c1), pack2(c2, 0.f), 0u, 0u);
                    }
                fence_async_smem();
                __syncwarp();
                if (one) {
                    bulk_store(g_xb + tile * 240, sbase + A1_SM_XB, 3840);
                    asm volatile("cp.async.bulk.commit_group;" ::: "memory");
                    asm volatile("cp.async.bulk.wait_group.read 0;" ::: "memory");
                    mbar_arrive(bar_stat);
                }
                __syncwarp();
                CSA(1);
            }
            TSTAMP1T(9, 288);
        } else {
            const int j = tid - 320;
            const uint32_t tag = ld_epoch();
            if (tid == 352) sm_started(layer);
            const int ch = j & 7, kg = (j >> 3) & 3;
            const unsigned char* src = stg + (layer ? (j >> 5) * 8192 + (hg & 3) * 2048 : A1_SM_W0 + (j >> 2) * 1280);
            const int of0 = layer ? kg * 128 + ((ch ^ kg) << 4) : (j & 7) << 4, ofx = layer ? 576 : 64, ofy = layer ? 1024 : 128;
            float s[8], q[8], p0[8];
#pragma unroll
            for (int i = 0; i < 8; i++) { s[i] = 0.f; q[i] = 0.f; }
#pragma unroll 1
            for (int it = 0; it < 5; it++) {
                uint4 v[4];
                mbar_wait(layer ? bars + 8 * (it % A1_NST) : bars + 240, layer * it / A1_NST);
#pragma unroll
                for (int k = 0; k < 4; k++) v[k] = *reinterpret_cast<const uint4*>(src + (layer ? (it % A1_NST) * A1_STAGE : it * 256) + (k & 1 ? of0 ^ ofx : of0) + (k >> 1) * ofy);
                if (it == 0) {
                    const uint4 pv = *reinterpret_cast<const uint4*>(src + (layer ? ch << 4 : 0));
                    const uint32_t w[4] = {pv.x, pv.y, pv.z, pv.w};
#pragma unroll
                    for (int i = 0; i < 4; i++) { p0[2 * i] = __uint_as_float((layer ? w[i] : w[0]) << 16); p0[2 * i + 1] = __uint_as_float(layer ? w[i] & 0xffff0000u : w[0] << 16); }
                }
                asm volatile("" :: "r"(v[0].x), "r"(v[1].x), "r"(v[2].x), "r"(v[3].x), "f"(p0[0]) : "memory");
                __syncwarp();
                if ((tid & 31) == 0) mbar_arrive(bar_rd + 8 * it);
#pragma unroll
                for (int k = 0; k < 4; k++) {
                    const uint32_t w[4] = {v[k].x, v[k].y, v[k].z, v[k].w};
#pragma unroll
                    for (int i = 0; i < 4; i++) {
                        const float a = __uint_as_float(w[i] << 16) - p0[2 * i], b = __uint_as_float(w[i] & 0xffff0000u) - p0[2 * i + 1];
                        s[2 * i] += a; s[2 * i + 1] += b; q[2 * i] = fmaf(a, a, q[2 * i]); q[2 * i + 1] = fmaf(b, b, q[2 * i + 1]);
                    }
                }
            }
            float o[4];
            int row;
            if (layer == 0) {
                float s0 = ((s[0] + s[1]) + (s[2] + s[3])) + ((s[4] + s[5]) + (s[6] + s[7])), q0 = ((q[0] + q[1]) + (q[2] + q[3])) + ((q[4] + q[5]) + (q[6] + q[7]));
#pragma unroll
                for (int o = 1; o <= 2; o <<= 1) { s0 += __shfl_xor_sync(~0u, s0, o); q0 += __shfl_xor_sync(~0u, q0, o); }
                if ((j & 3) == 0) {
                    const float d = s0 * (1.0f / DM);
                    const uint32_t ms = pack2(p0[0] + d, sqrt_apx(rbf(rbf(fmaxf(fmaf(-d, d, q0 * (1.0f / DM)), 0.f)) + 1e-5f)));
                    asm volatile("st.global.cg.u64 [%0], %1;" ::"l"(g_rstat + mb * 128 + (j & 4) * 16 + hg * 8 + (j >> 3)), "l"(tagw(ms, tag)) : "memory");
                    g_piv[mb * 128 + hg * 16 + ((j >> 2) & 8) + (j & 4) + ((j >> 3) & 3)] = __ushort_as_bfloat16((unsigned short)ms);
                }
                ulonglong2 v;
#pragma unroll 1
                for (int it = 0; it < SPIN_MAX; it++) {
                    v = ld_tag2(reinterpret_cast<const ulonglong2*>(g_rstat + mb * 128) + j);
                    if (__all_sync(~0u, tag_ok(v, tag))) break;
                    __nanosleep(100);
                }
                o[0] = __uint_as_float((uint32_t)v.x << 16); o[1] = rcp_apx(__uint_as_float((uint32_t)v.x & 0xffff0000u));
                o[2] = __uint_as_float((uint32_t)v.y << 16); o[3] = rcp_apx(__uint_as_float((uint32_t)v.y & 0xffff0000u));
                row = 2 * j;
            } else {
#pragma unroll
                for (int i = 0; i < 4; i++) {
                    const bool up = kg & 2;
                    const float ss = __shfl_xor_sync(~0u, up ? s[i] : s[i + 4], 16), qq = __shfl_xor_sync(~0u, up ? q[i] : q[i + 4], 16);
                    s[i] = (up ? s[i + 4] : s[i]) + ss; q[i] = (up ? q[i + 4] : q[i]) + qq; p0[i] = up ? p0[i + 4] : p0[i];
                }
#pragma unroll
                for (int i = 0; i < 2; i++) {
                    const bool up = kg & 1;
                    const float ss = __shfl_xor_sync(~0u, up ? s[i] : s[i + 2], 8), qq = __shfl_xor_sync(~0u, up ? q[i] : q[i + 2], 8);
                    s[i] = (up ? s[i + 2] : s[i]) + ss; q[i] = (up ? q[i + 2] : q[i]) + qq; p0[i] = up ? p0[i + 2] : p0[i];
                }
                uint4* gp = g_halo + 86016 + mb * 512 + j;
                const float d0 = s[0] * (1.0f / 80.0f), d1 = s[1] * (1.0f / 80.0f);
                asm volatile("st.relaxed.gpu.global.v4.f32 [%0], {%1,%2,%3,%4};" ::"l"(gp + hg * 64), "f"(p0[0] + d0), "f"(fmaxf(fmaf(-d0, s[0], q[0]), 0.f)), "f"(p0[1] + d1), "f"(fmaxf(fmaf(-d1, s[1], q[1]), 0.f)) : "memory");
                __nanosleep(ST_SLEEP0);
                uint32_t pw[8][4], todo = 0xff;
#pragma unroll 1
                for (int it = 0; it < SPIN_MAX; it++) {
#pragma unroll
                    for (int k = 0; k < 8; k++)
                        if (todo >> k & 1) asm volatile("ld.relaxed.gpu.global.v4.u32 {%0,%1,%2,%3}, [%4];" : "=r"(pw[k][0]), "=r"(pw[k][1]), "=r"(pw[k][2]), "=r"(pw[k][3]) : "l"(gp + k * 64) : "memory");
#pragma unroll
                    for (int k = 0; k < 8; k++)
                        if (__all_sync(~0u, pw[k][0] != ~0u && pw[k][1] != ~0u && pw[k][2] != ~0u && pw[k][3] != ~0u)) todo &= ~(1u << k);
                    if (!todo) break;
                    __nanosleep(ST_SLEEP);
                }
#pragma unroll
                for (int r = 0; r < 2; r++) {
                    float mean = 0.f, m2 = 0.f;
#pragma unroll
                    for (int k = 0; k < 8; k++) mean += __uint_as_float(pw[k][2 * r]);
                    mean *= 0.125f;
#pragma unroll
                    for (int k = 0; k < 8; k++) {
                        const float dm = __uint_as_float(pw[k][2 * r]) - mean;
                        m2 += fmaf(80.0f * dm, dm, __uint_as_float(pw[k][2 * r + 1]));
                    }
                    o[2 * r] = rbf(mean);
                    o[2 * r + 1] = rcp_apx(rbf(sqrt_apx(rbf(rbf(m2 * (1.0f / DM)) + 1e-5f))));
                }
                row = (j >> 5) * 64 + (j & 7) * 8 + ((j >> 3) & 3) * 2;
                if (hg == 0) *reinterpret_cast<uint32_t*>(g_piv + SEQ + mb * 128 + 2 * (row & 60) + 4 * (row >> 6) + (row & 3)) = __byte_perm(__float_as_uint(o[0]), __float_as_uint(o[2]), 0x7632);
            }
#pragma unroll
            for (int r = 0; r < 2; r++)
                *reinterpret_cast<uint4*>(stg + A1_SM_XA + (row + r) * 16) = make_uint4(__byte_perm(__float_as_uint(-o[2 * r]), 0, 0x3232), __float_as_uint(-o[2 * r]) >> 16, 0u, 0u);
            *reinterpret_cast<float4*>(rst + row + (row >> 6) * 8) = make_float4(o[0], o[1], o[2], o[3]);
            fence_async_smem();
            TSTAMP1T(7, 320); CSA(1);
            if (tid == 320) DBGC(44);
            __syncwarp();
            if ((tid & 31) == 0) mbar_arrive(bar_stat);
        }
        CSA(4); CSA_END;
        if (tid == 320) DBGCAL(0);
        __syncwarp();
        if (w == WOT) {
            mbar_wait(bars + 416, 0);
            mbar_wait(bar_done, 0);
            if (one) {
                bulk_load(sbase, wo + (hg * 8 + 6) * WOB, 2 * WOB, bar_wo);
                bulk_load(sbase + A1_SM_W0 + 2 * WOB, wo + (hg * 8 + 2) * WOB, WOB, bar_wo);
            }
            __syncwarp();
        }
#define FWA 11
#define FWB 10
        if (w == FWA || w == FWB) {
            const int cw = w == FWB;
            const uint32_t* fl = reinterpret_cast<const uint32_t*>(rsum + 2 * SEQ) + (((layer * 16 + mb) * 2 + cw) * 8 + (tid & 7)) * FSTR;
            const unsigned char* src = reinterpret_cast<const unsigned char*>(of) + mb * 163840 + cw * 10240 + (tid & 7) * 20480;
            const uint32_t sl = sbase + (cw ? A1_SM_A1 : A1_SM_A0);
            mbar_wait(cw ? bar_done : bar_kvf, 0);
            if (one) {
                mbar_expect_tx(bar_f2 + 64 * cw + 64, 10240);
                tma_load_3d(sl + 51200, &tmR, layer ? 0 : hg * 80, layer ? hg * 80 : mb * 64, layer ? mb * 2 + cw : cw, bar_f2 + 64 * cw + 64);
            }
            __syncwarp();
            uint32_t pend = 0xffu & ~(1u << hg), v = 0;
            const uint32_t bo = wo_off((tid & 7) + ((tid & 7) < hg)) >> 4, lt = (1u << (tid & 31)) - 1;
#pragma unroll 1
            for (int it = 0; pend && it < 2 * SPIN_MAX; it++) {
                if (v != 4 && (pend >> (tid & 31) & 1)) asm volatile(A1_FLD " %0, [%1];" : "=r"(v) : "l"(fl) : "memory");
                uint32_t fr;
                asm volatile("{\n.reg .pred p;\nmbarrier.test_wait.parity.shared::cta.b64 p, [%1], 0;\nselp.b32 %0, 1, 0, p;\n}" : "=r"(fr) : "r"(bar_e2 + 16 * cw + (tid & 1) * 8) : "memory");
                fr = __ballot_sync(~0u, fr);
                uint32_t m = __ballot_sync(~0u, v == 4 || it >= A1_FSPIN) & pend;
                const int q = 8 - __popc(pend) + __popc(m & lt);
                m &= __ballot_sync(~0u, q < ((fr & 2) ? 8 : (fr & 1) ? 7 : 5));
                pend ^= m;
                if (m >> (tid & 31) & 1) DBGC(12 + cw * 8 + (tid & 7));
                if (!m) __nanosleep(A1_FSLEEP);
                if (m >> (tid & 31) & 1) {
                    bulk_load(q == 7 && !cw ? sbase + A1_SM_W0 : sl + (q < 6 ? q : q - 6) * 10240, src, 10240, bar_f2 + 64 * cw + 8 * q);
                    asm volatile("st.shared.u32 [%0], %1;" ::"r"(que + 32 * cw + 4 * q), "r"(bo) : "memory");
                    mbar_expect_tx(bar_f2 + 64 * cw + 8 * q, 10240);
                    DBGC(44 + cw * 8 + q);
                }
                __syncwarp();
            }
        }
    } else if (tile < 128) {
        SPAN(1 + 4 * layer, 0);
        constexpr int on = 1;
        float acc[120];
        const int lane = tid & 31, warp = w & 7, g = lane >> 2, t = lane & 3;
        if (on) {
            SPAN(1 + 4 * layer, 1);
            TSTAMP1(0);
            if (threadIdx.x == 0) { GSTAMP(g_tim1, 15); }
            TSTAMP3(0);
            if (tid == 0) TSTAMP2(0);
            TSTAMP4(0);
            if (tid == 0) DBGC(60);
            if (layer == 0) a1_mainloop<0>(acc, sbase, bars, wg, tile); else a1_mainloop<1>(acc, sbase, bars, wg, tile);
            uint32_t ok;
            asm volatile("{\n.reg .pred p;\nmbarrier.test_wait.parity.shared::cta.b64 p, [%1], 0;\nselp.b32 %0, 1, 0, p;\n}" : "=r"(ok) : "r"(bar_stat) : "memory");
            if (tid == 128 && !ok) mbar_arrive(bars + 160);
            __syncwarp();
            mbar_wait(bar_stat, 0);
            wgmma_fence();
            wgmma_n240<0, 0>(acc, make_desc(sbase + A1_SM_XA + wg * 1024, 0, 128, 0), make_desc(sbase + A1_SM_XB, 0, 128, 0), 1);
            wgmma_commit();
            if (tid == 128 && ok) mbar_arrive(bars + 160);
            mbar_wait(bars + 8 * (A1_NST + 3), 1);
        }
        uint4* hp = g_halo + (((layer * 16 + mb - ((warp & 3) != 3)) * 8 + hg) * 2 + wg) * 168 + lane;
        float* hr = reinterpret_cast<float*>(hp - lane + 160) + ((warp & 3) == 3 ? g : 2 * t);
        asm volatile("" : "+l"(hp), "+l"(hr));
        const float2* rw = rst + 16 * warp + 8 * wg;
        const float rb0 = rw[g + 8].y, ra = rw[g].y * 0.22360679774997896f, rb = rb0 * 0.22360679774997896f;
        wgmma_wait<0>();
        if ((tid & 127) == 0) mbar_arrive(bar_done);
        TSTAMP1(2); CSA(1);
        TSTAMP1T(13, 224);
        if ((tid & 127) == 0) DBGC(62 - wg);
        uint32_t f[2][30];
#pragma unroll
        for (int j = 10; j < 30; j++) f[1][j] = pack2(acc[4 * j + 2], acc[4 * j + 3]);
        if ((warp & 3) == 3) {
#pragma unroll
            for (int j = 0; j < 20; j += 4) {
                const int a = j < 12 ? 10 + j : 8 + j, b = j == 8 ? 28 : a + 2;
                asm volatile("st.relaxed.gpu.global.v4.u32 [%0], {%1,%2,%3,%4};" ::"l"(hp + 8 * j), "r"(f[1][a]), "r"(f[1][a + 1]), "r"(f[1][b]), "r"(f[1][b + 1]) : "memory");
            }
            if (t == 0) asm volatile("st.relaxed.gpu.global.f32 [%0], %1;" ::"l"(hr), "f"(rb0) : "memory");
        }
        TSTAMP1T(12, 224);
        const uint32_t kvw = sbase + A1_SM_KV + (16 * warp + 8 * wg) * A1_KVP;
        const uint32_t mrow = kvw + (lane & 7) * A1_KVP + (lane >> 3) * 16;
#pragma unroll
        for (int j = 0; j < 20; j += 4) {
            const int a = j < 12 ? 10 + j : 8 + j, b = j == 8 ? 28 : a + 2;
            stsm_x4(mrow + 16 * A1_KVP + 16 * (a - 10) + (j == 8 ? (lane & 16) * 8 : 0), f[1][a], f[1][a + 1], f[1][b], f[1][b + 1]);
        }
        __syncwarp();
        if (lane == 0 && (warp & 3) != 3) mbar_arrive(bar_kv + 8 * (warp + 1));
#pragma unroll
        for (int j = 0; j < 30; j++) f[0][j] = pack2(acc[4 * j], acc[4 * j + 1]);
        stsm_x4(mrow + 8 * A1_KVP + 160, f[0][20], f[0][21], f[0][22], f[0][23]);
        stsm_x4(mrow + 8 * A1_KVP + 224, f[0][24], f[0][25], f[0][26], f[0][27]);
        asm volatile("stmatrix.sync.aligned.m8n8.x2.shared.b16 [%0], {%1,%2};" ::"r"(mrow + 8 * A1_KVP + 288), "r"(f[0][28]), "r"(f[0][29]) : "memory");
#pragma unroll
        for (int j = 0; j < 10; j++) f[1][j] = pack2(acc[4 * j + 2], acc[4 * j + 3]);
        __syncwarp();
        uint32_t vb[10][2], hv[24] = {}, *kp = hv, *vp = hv + 12;
#pragma unroll
        for (int j = 0; j < 10; j += 2) ldsm_x4_t(&vb[j][0], kvw + (8 + (lane & 15)) * A1_KVP + 160 + (lane >> 4) * 16 + 16 * j);
        const bool up0 = 2 * t > g, up1 = 2 * t + 1 > g, edge = (mb | (warp & 3)) == 0;
        float rk[4];
        auto above = [&]() {
            mbar_wait(bar_kv + 8 * warp, 0);
#pragma unroll
            for (int j = 0; j < 12; j += 4) ldsm_x4(&kp[j], mrow + 16 * j);
            rk[0] = rw[2 * t - (up0 ? 8 : 0)].y; rk[1] = rw[2 * t + 1 - (up1 ? 8 : 0)].y;
#pragma unroll
            for (int j = 0; j < 8; j += 4) ldsm_x4_t(&vp[j], mrow + 160 + 16 * j);
            asm volatile("ldmatrix.sync.aligned.m8n8.x2.trans.shared.b16 {%0,%1}, [%2];" : "=r"(vp[8]), "=r"(vp[9]) : "r"(mrow + 288) : "memory");
            __syncwarp();
            if (lane == 0) mbar_arrive(bar_kvf);
        };
        auto ask = [&]() {
            if (mb > 0) {
#pragma unroll
                for (int k = 0; k < 20; k += 4)
                    asm volatile("ld.relaxed.gpu.global.v4.u32 {%0,%1,%2,%3}, [%4];" : "=r"(hv[k]), "=r"(hv[k + 1]), "=r"(hv[k + 2]), "=r"(hv[k + 3]) : "l"(hp + 8 * k) : "memory");
                asm volatile("ld.relaxed.gpu.global.v2.u32 {%0,%1}, [%2];" : "=r"(hv[20]), "=r"(hv[21]) : "l"(hr) : "memory");
            }
        };
        auto halo = [&]() {
            if (lane == 0) mbar_arrive(bar_kvf);
            rk[0] = rw[2 * t].y; rk[1] = rw[2 * t + 1].y;
#pragma unroll 1
            for (int it = 0; it < SPIN_MAX; it++) {
                uint32_t m = max(hv[20], hv[21]);
#pragma unroll
                for (int k = 0; k < 20; k += 2) m = __vimax3_u32(m, hv[k], hv[k + 1]);
                if (!__any_sync(~0u, m == ~0u)) break;
                ask();
            }
            if (wg && lane == 0) mbar_arrive(bars + 416);
            if (up0) rk[0] = __uint_as_float(hv[20]);
            if (up1) rk[1] = __uint_as_float(hv[21]);
#pragma unroll
            for (int j = 0; j < 10; j++) asm volatile("movmatrix.sync.aligned.m8n8.trans.b16 %0, %1;" : "=r"(vp[j]) : "r"(hv[j < 8 ? 12 + j : 2 + j]));
        };
        rk[2] = rw[2 * t + (up0 ? 0 : 8)].y; rk[3] = rw[2 * t + 1 + (up1 ? 0 : 8)].y;
        uint32_t qs[4][2];
#pragma unroll
        for (int h = 0; h < 4; h++) {
            qs[h][0] = (t >> 1) == (h & 1) ? f[0][5 * (h >> 1) + 2] : 0u; qs[h][1] = (t >> 1) == (h & 1) ? f[1][5 * (h >> 1) + 2] : 0u;
            asm volatile("" : "+r"(qs[h][0]), "+r"(qs[h][1]));
        }
#pragma unroll
        for (int j = 0; j < 10; j++) asm volatile("" : "+r"(f[0][j]), "+r"(f[1][j]), "+r"(f[0][10 + j]));
        if (warp & 3) above(); else if (wg) ask(); else hv[20] = mb ? ~0u : 0u;
        TSTAMP1T(10, 64); CSA(2);
        if (warp && !wg) mbar_wait(bars + 416 + 8 * warp, 0);
        CSA(3);
        float sc[4][3][4];
#pragma unroll
        for (int h = 0; h < 4; h++) {
            const int jb = 5 * (h >> 1) + 3 * (h & 1), js = 5 * (h >> 1) + 2;
#pragma unroll
            for (int nt = 1; nt < 3; nt++) {
#pragma unroll
                for (int e = 0; e < 4; e++) sc[h][nt][e] = 0.f;
                mma_bf16(sc[h][nt], f[0][jb], f[1][jb], f[0][jb + 1], f[1][jb + 1], f[nt - 1][10 + jb], f[nt - 1][11 + jb]);
                mma_bf16_k8(sc[h][nt], qs[h][0], qs[h][1], f[nt - 1][10 + js]);
            }
        }
        if (!(warp & 3)) halo();
        TSTAMP1(8); CSA(4);
#pragma unroll
        for (int h = 0; h < 4; h++) {
            const int jb = 5 * (h >> 1) + 3 * (h & 1), js = 5 * (h >> 1) + 2;
#pragma unroll
            for (int e = 0; e < 4; e++) sc[h][0][e] = 0.f;
            mma_bf16(sc[h][0], f[0][jb], f[1][jb], f[0][jb + 1], f[1][jb + 1], kp[jb], kp[jb + 1]);
            mma_bf16_k8(sc[h][0], qs[h][0], qs[h][1], kp[js]);
        }
        TSTAMP1T(3, 64);
        float p[4][4], sum[4][2];
        uint32_t lg[4][2], mx[4];
        const float rl[4] = {rk[0] * ra, rk[1] * ra, rk[2] * rb, rk[3] * rb};
        auto max2 = [](uint32_t a, uint32_t b) { uint32_t r; asm("max.bf16x2 %0, %1, %2;" : "=r"(r) : "r"(a), "r"(b)); return r; };
#pragma unroll
        for (int h = 0; h < 4; h++) {
            lg[h][0] = pack2((up0 ? sc[h][0][0] : sc[h][1][0]) * rl[0], (up0 ? sc[h][1][2] : sc[h][2][2]) * rl[2]);
            lg[h][1] = pack2((up1 ? sc[h][0][1] : sc[h][1][1]) * rl[1], (up1 ? sc[h][1][3] : sc[h][2][3]) * rl[3]);
            if (edge) {
                if (up0) lg[h][0] = __byte_perm(lg[h][0], 0xce6eu, 0x3254);
                if (up1) lg[h][1] = __byte_perm(lg[h][1], 0xce6eu, 0x3254);
            }
            mx[h] = max2(lg[h][0], lg[h][1]);
        }
#pragma unroll
        for (int o = 1; o <= 2; o <<= 1)
#pragma unroll
            for (int h = 0; h < 4; h++) mx[h] = max2(mx[h], __shfl_xor_sync(~0u, mx[h], o));
#pragma unroll
        for (int h = 0; h < 4; h++)
#pragma unroll
            for (int r = 0; r < 2; r++) {
                const float m = __uint_as_float(r ? mx[h] & 0xffff0000u : mx[h] << 16);
#pragma unroll
                for (int e = 0; e < 2; e++)
                    asm("ex2.approx.ftz.f32 %0, %1;" : "=f"(p[h][2 * r + e]) : "f"((__uint_as_float(r ? lg[h][e] & 0xffff0000u : lg[h][e] << 16) - m) * 1.4426950408889634f));
                sum[h][r] = p[h][2 * r] + p[h][2 * r + 1];
            }
#pragma unroll
        for (int o = 1; o <= 2; o <<= 1)
#pragma unroll
            for (int h = 0; h < 4; h++)
#pragma unroll
                for (int r = 0; r < 2; r++) sum[h][r] += __shfl_xor_sync(~0u, sum[h][r], o);
        TSTAMP1T(5, 64); CSA(5);
        const uint32_t mu = (up0 ? 0xffffu : 0u) | (up1 ? 0xffff0000u : 0u);
        uint32_t ob[10][2];
#pragma unroll
        for (int P = 0; P < 2; P++) {
            float os[2][4];
#pragma unroll
            for (int e = 0; e < 2; e++) {
                const int h = 2 * P + e;
                const float i0 = rcp_apx(sum[h][0]), i1 = rcp_apx(sum[h][1]);
                const uint32_t w0 = pack2(p[h][0] * rk[0] * i0, p[h][1] * rk[1] * i0), w1 = pack2(p[h][2] * rk[2] * i1, p[h][3] * rk[3] * i1);
#pragma unroll
                for (int dt = 0; dt < 3; dt++) {
                    const int j = 5 * P + (dt < 2 ? 3 * e + dt : 2);
                    float o[4] = {0.f, 0.f, 0.f, 0.f};
                    mma_bf16(o, w0 & ~mu, w1 & mu, 0u, w1 & ~mu, vb[j][0], vb[j][1]);
                    mma_bf16_k8(o, w0 & mu, 0u, vp[j]);
                    if (dt < 2) { ob[j][0] = pack2(o[0], o[1]); ob[j][1] = pack2(o[2], o[3]); }
                    else { os[e][0] = o[0]; os[e][1] = o[1]; os[e][2] = o[2]; os[e][3] = o[3]; }
                }
            }
#pragma unroll
            for (int k = 0; k < 4; k++) os[0][k] = t < 2 ? os[0][k] : os[1][k];
            ob[5 * P + 2][0] = pack2(os[0][0], os[0][1]); ob[5 * P + 2][1] = pack2(os[0][2], os[0][3]);
        }
        const uint32_t sl = sbase + (wg ? A1_SM_A1 : A1_SM_A0);
        const uint32_t o0 = (warp & 3) * 2048 + g * 64 + ((t ^ (g >> 1)) << 4), o1 = 8192 + (warp & 3) * 512 + g * 32 + ((t ^ ((g >> 2) << 1)) << 3);
        CSA(15);
#pragma unroll
        for (int j = 0; j < 10; j++) asm volatile("" : "+r"(ob[j][0]), "+r"(ob[j][1]) :: "memory");
        if (wg == 0 && lane == 0) mbar_arrive(bar_pv);
        mbar_wait(bar_done, 0);
        if (wg == 0) mbar_wait(bar_kvf, 0);
#pragma unroll
        for (int h = 0; h < 2; h++) {
            asm volatile("st.shared.v4.u32 [%0], {%1,%2,%3,%4};" ::"r"(sl + o0 + h * 1024), "r"(ob[0][h]), "r"(ob[1][h]), "r"(ob[2][h]), "r"(ob[3][h]) : "memory");
            asm volatile("st.shared.v4.u32 [%0], {%1,%2,%3,%4};" ::"r"(sl + o0 + h * 1024 + 512), "r"(ob[4][h]), "r"(ob[5][h]), "r"(ob[6][h]), "r"(ob[7][h]) : "memory");
            asm volatile("st.shared.v2.u32 [%0], {%1,%2};" ::"r"(sl + o1 + h * 256), "r"(ob[8][h]), "r"(ob[9][h]) : "memory");
        }
        if (warp > 4 && lane == 0) mbar_arrive(bars + 384 + 8 * warp);
        fence_async_smem();
        __syncwarp();
        TSTAMP1T(4, 64); CSA(6);
        TSTAMP1(1);
        TSTAMP2(1);
        const unsigned char* ot = reinterpret_cast<const unsigned char*>(of) + mb * 163840 + wg * 10240;
        if (lane == 0) {
            asm volatile("cp.async.bulk.global.shared::cta.bulk_group [%0], [%1], 2048;" ::"l"(ot + hg * 20480 + (warp & 3) * 2048), "r"(sl + (warp & 3) * 2048) : "memory");
            asm volatile("cp.async.bulk.global.shared::cta.bulk_group [%0], [%1], 512;" ::"l"(ot + hg * 20480 + 8192 + (warp & 3) * 512), "r"(sl + 8192 + (warp & 3) * 512) : "memory");
            asm volatile("cp.async.bulk.commit_group;" ::: "memory");
            asm volatile("cp.async.bulk.wait_group 0;" ::: "memory");
            asm volatile(A1_FRED " [%0], 1;" ::"l"(reinterpret_cast<uint32_t*>(rsum + 2 * SEQ) + (((layer * 16 + mb) * 2 + wg) * 8 + hg) * FSTR) : "memory");
            DBGC(4 + warp);
        }
        TSTAMP4(11); CSA(7);
        float ac2[40];
        const uint64_t db0 = make_desc(sbase, 1024, 256, 3), db1 = make_desc(sbase + 10240, 512, 256, 3), da0 = make_desc(sl, 16, 1024, 2), da1 = make_desc(sl + 8192, 16, 256, 3);
        const uint32_t o7 = wg ? 640 : (A1_SM_W0 - A1_SM_A0) >> 4;
        const uint32_t trow = ((lane & 7) + 8 * (lane >> 4)) * 128 + (((2 * (warp & 3) + ((lane >> 3) & 1)) ^ (lane & 7)) << 4);
        uint32_t xr[10][2];
        mbar_wait(bar_f2 + 64 * wg + 64, 0);
        if (layer == 0) {
#pragma unroll
            for (int j = 0; j < 10; j += 2) ldsm_x4(&xr[j][0], sl + 51200 + (16 * (warp & 3) + (lane & 15)) * 160 + (lane >> 4) * 16 + 16 * j);
        } else {
#pragma unroll
            for (int j = 0; j < 10; j += 2) ldsm_x4_t(&xr[j][0], sl + 51200 + trow + 1024 * j);
        }
        const uint32_t ri = __shfl_sync(~0u, layer * SEQ + (wg * 2 + ((g >> 1) & 1)) * 512 + (mb * 16 + 4 * (warp & 3) + (g >> 2)) * 2 + (g & 1), lane);
        mbar_wait(bar_wo, 0);
        if (wg) asm volatile("bar.sync 2, 128;" ::: "memory"); else asm volatile("bar.sync 1, 128;" ::: "memory");
        if (wg) mbar_wait(bar_pv, 0);
        TSTAMP2(2); CSA(8);
#pragma unroll
        for (int q = 0; q < 8; q++) {
            uint32_t bo = wo_off(0) >> 4;
            if (q) {
                mbar_wait(bar_f2 + 64 * wg + 8 * q, 0);
                asm volatile("ld.shared.u32 %0, [%1];" : "=r"(bo) : "r"(que + 32 * wg + 4 * q) : "memory");
                bo = __shfl_sync(~0u, bo, 0);
                TSTAMP4(q);
                if (q % 3 == 1) CSA(9 + q / 3);
                if (q == 1 && (tid & 127) == 0) DBGC(29 + 8 * wg);
            }
            wgmma_fence();
#pragma unroll
            for (int j = 0; j < 5; j++) wgmma_n80(ac2, (j < 4 ? da0 : da1) + (q == 7 ? o7 : 0u) + (uint64_t)((q < 6 ? q * 640 : 0) + (j & 2) * 16 + (j & 1) * 2), (j < 4 ? db0 : db1) + bo + (uint64_t)((j & 2) * 160 + (j & 1) * 32), j || q);
            wgmma_commit();
            if (q == 0) {
                wgmma_wait<0>();
                if ((tid & 127) == 0) { mbar_arrive(bar_e2 + 16 * wg); mbar_arrive(bar_e2 + 8); }
            }
            if (q == 2 && wg) {
                wgmma_wait<1>();
                if (tid == 128) mbar_arrive(bar_e2 + 24);
            }
        }
        if ((tid & 127) == 0) DBGC(28 + wg * 8 + 7);
        TSTAMP2(3);
        wgmma_wait<0>();
        TSTAMP2(4); CSA(12);
        if (__any_sync(~0u, ac2[0] != ac2[0] || ac2[2] != ac2[2])) {
#pragma unroll
            for (int i = 0; i < 40; i++) ac2[i] = 0.f;
            uint32_t a[20], an[20];
            auto lda = [&](uint32_t (&r)[20], int h) {
#pragma unroll
                for (int u = 0; u < 4; u++)
                    asm volatile("ld.relaxed.gpu.global.v4.u32 {%0,%1,%2,%3}, [%4];" : "=r"(r[4 * u]), "=r"(r[4 * u + 1]), "=r"(r[4 * u + 2]), "=r"(r[4 * u + 3]) : "l"(ot + h * 20480 + o0 + u * 512) : "memory");
#pragma unroll
                for (int u = 0; u < 2; u++)
                    asm volatile("ld.relaxed.gpu.global.v2.u32 {%0,%1}, [%2];" : "=r"(r[16 + 2 * u]), "=r"(r[17 + 2 * u]) : "l"(ot + h * 20480 + o1 + u * 256) : "memory");
            };
            lda(an, 0);
#pragma unroll 5
            for (int k = lane; k < WOB / 16; k += 32)
                reinterpret_cast<uint4*>(stg + (sl - sbase))[k] = __ldcg(reinterpret_cast<const uint4*>(wo + hg * 8 * WOB) + k);
            __syncwarp();
#pragma unroll 1
            for (int h = 0; h < 8; h++) {
#pragma unroll 1
                for (int it = 0; it < SPIN_MAX; it++) {
                    uint32_t m = 0;
#pragma unroll
                    for (int k = 0; k < 20; k += 2) m = __vimax3_u32(m, an[k], an[k + 1]);
                    if (!__any_sync(~0u, m == ~0u)) break;
                    lda(an, h);
                }
#pragma unroll
                for (int k = 0; k < 20; k++) a[k] = an[k];
                lda(an, min(h + 1, 7));
                const uint32_t bp = h == hg ? sl : sbase + wo_off(h + (h < hg));
                const int r0 = 8 * ((lane & 7) >> 1) + 2 * (lane >> 3) + (lane & 1), r2 = 4 * ((lane & 7) >> 1) + 2 * ((lane >> 3) & 1) + (lane & 1);
#pragma unroll
                for (int n = 0; n < 10; n++) {
                    uint32_t b[12];
                    ldsm_x4_t(b, bp + (n >> 1) * 1024 + r0 * 32 + (((n ^ (r0 >> 2)) & 1) << 4));
                    ldsm_x4_t(b + 4, bp + 5120 + (n >> 1) * 1024 + r0 * 32 + (((n ^ (r0 >> 2)) & 1) << 4));
                    ldsm_x4_t(b + 8, bp + 10240 + (n >> 1) * 512 + r2 * 32 + (((n ^ (r2 >> 2)) & 1) << 4));
                    mma_bf16(ac2 + 4 * n, a[0], a[8], a[1], a[9], b[0], b[1]); mma_bf16(ac2 + 4 * n, a[2], a[10], a[3], a[11], b[2], b[3]);
                    mma_bf16(ac2 + 4 * n, a[4], a[12], a[5], a[13], b[4], b[5]); mma_bf16(ac2 + 4 * n, a[6], a[14], a[7], a[15], b[6], b[7]);
                    mma_bf16(ac2 + 4 * n, a[16], a[18], a[17], a[19], b[8], b[9]);
                }
            }
        }
#pragma unroll
        for (int j = 0; j < 10; j++)
#pragma unroll
            for (int hh = 0; hh < 2; hh++) {
                const uint32_t a = pack2(ac2[4 * j + 2 * hh], ac2[4 * j + 2 * hh + 1]);
                const __nv_bfloat162 r = __hadd2_rn(*reinterpret_cast<const __nv_bfloat162*>(&xr[j][hh]), *reinterpret_cast<const __nv_bfloat162*>(&a));
                xr[j][hh] = *reinterpret_cast<const uint32_t*>(&r);
            }
        const uint32_t so = sl + 30720;
#pragma unroll
        for (int j = 0; j < 10; j += 2) stsm_x4_t(so + trow + 1024 * j, xr[j][0], xr[j][1], xr[j + 1][0], xr[j + 1][1]);
        if (wg) asm volatile("bar.sync 2, 128;" ::: "memory"); else asm volatile("bar.sync 1, 128;" ::: "memory");
        TSTAMP2(5); CSA(13);
        if ((tid & 127) == 0) {
            fence_async_smem();
            asm volatile("cp.async.bulk.tensor.2d.global.shared::cta.bulk_group [%0, {%1, %2}], [%3];" ::"l"(&tmX1), "r"(mb * 128 + 64 * wg), "r"(hg * 80), "r"(so) : "memory");
            asm volatile("cp.async.bulk.commit_group;" ::: "memory");
        }
        __syncwarp();
        const float p0 = *(volatile const float*)&rw[g].x, p1 = *(volatile const float*)&rw[g + 8].x;
        float s[3][4] = {};
        const uint32_t pp[2] = {__byte_perm(__float_as_uint(p0), 0, 0x3232), __byte_perm(__float_as_uint(p1), 0, 0x3232)};
#pragma unroll
        for (int j = 0; j < 10; j += 2) {
            const uint32_t d0 = sub2(xr[j][0], pp[0]), d1 = sub2(xr[j][1], pp[1]), d2 = sub2(xr[j + 1][0], pp[0]), d3 = sub2(xr[j + 1][1], pp[1]);
            mma_bf16(s[0], xr[j][0], xr[j][1], xr[j + 1][0], xr[j + 1][1], 0x3f803f80u, 0x3f803f80u);
            mma_bf16(s[1], d0, d1, d2, d3, d0, d2);
            mma_bf16(s[2], d0, d1, d2, d3, d1, d3);
        }
        if (t == (g >> 1)) {
            float2* rp = rsum + ri;
            constexpr float idm = 1.0f / DM;
            asm volatile("red.relaxed.gpu.global.add.v2.f32 [%0], {%1, %2};" ::"l"(rp), "f"(fmaf(-80.f, p0, s[0][0]) * idm), "f"(((g & 1) ? s[1][1] : s[1][0]) * idm) : "memory");
            asm volatile("red.relaxed.gpu.global.add.v2.f32 [%0], {%1, %2};" ::"l"(rp + 4), "f"(fmaf(-80.f, p1, s[0][2]) * idm), "f"(((g & 1) ? s[2][3] : s[2][2]) * idm) : "memory");
        }
        asm volatile("cp.async.bulk.wait_group.read 0;" ::: "memory");
        TSTAMP2(6); CSA(14); CSA_END;
        if (tid == 0) DBGC(63);
        if (tid == 128) DBGC(28);
        if (tid == 0) DBGCAL(2);
        GSTAMP(g_tim1, 14);
        SPAN(1 + 4 * layer, 3);
    }
#undef layer
}

static int h_nsm;
static void* h_sym[11];
static TileTab h_tab[2];
static CUtensorMap h_tmX0, h_tmX1, h_tmR0, h_tmR1, h_tmX1st, h_tmOut;
static KgMaps h_tmW;
typedef CUresult (*PFN_encodeTiled)(CUtensorMap*, CUtensorMapDataType, cuuint32_t, void*, const cuuint64_t*, const cuuint64_t*,
                                    const cuuint32_t*, const cuuint32_t*, CUtensorMapInterleave, CUtensorMapSwizzle,
                                    CUtensorMapL2promotion, CUtensorMapFloatOOBfill);
static void make_tmap(CUtensorMap* tm, const void* ptr, uint64_t cols, uint64_t rows, uint32_t bc, uint32_t br, CUtensorMapSwizzle sw, uint64_t pitch = 0, uint64_t hi = 0, uint32_t bh = 2) {
    static PFN_encodeTiled fn = nullptr;
    if (!fn) {
        void* p = nullptr; cudaDriverEntryPointQueryResult qr;
        cudaGetDriverEntryPoint("cuTensorMapEncodeTiled", &p, cudaEnableDefault, &qr);
        fn = (PFN_encodeTiled)p;
    }
    if (br == 0) {
        cuuint64_t dims[5] = {16, 2, rows / 8, 4, cols / 16}; cuuint64_t strides[4] = {cols * 2, cols * 16, cols * 4, 32};
        cuuint32_t box[5] = {16, 2, bc, 4, 5}; cuuint32_t es[5] = {1, 1, 1, 1, 1};
        fn(tm, CU_TENSOR_MAP_DATA_TYPE_BFLOAT16, 5, const_cast<void*>(ptr), dims, strides, box, es, CU_TENSOR_MAP_INTERLEAVE_NONE, sw,
           CU_TENSOR_MAP_L2_PROMOTION_L2_128B, CU_TENSOR_MAP_FLOAT_OOB_FILL_NONE);
        return;
    }
    if (hi == 16) {
        cuuint64_t dims[4] = {16, 32, 120, 20}; cuuint64_t strides[3] = {3840, 32, 32 * 3840};
        cuuint32_t box[4] = {16, 32, 5, 2}; cuuint32_t es[4] = {1, 1, 1, 1};
        fn(tm, CU_TENSOR_MAP_DATA_TYPE_BFLOAT16, 4, const_cast<void*>(ptr), dims, strides, box, es, CU_TENSOR_MAP_INTERLEAVE_NONE, sw,
           CU_TENSOR_MAP_L2_PROMOTION_L2_128B, CU_TENSOR_MAP_FLOAT_OOB_FILL_NONE);
        return;
    }
    if (bh == 0) {
        cuuint64_t dims[5] = {64, 64, 2, 16, 10}; cuuint64_t strides[4] = {pitch * 2, hi * 2, cols * 2, rows * 2};
        cuuint32_t box[5] = {64, 64, 2, 1, 1}; cuuint32_t es[5] = {1, 1, 1, 1, 1};
        fn(tm, CU_TENSOR_MAP_DATA_TYPE_BFLOAT16, 5, const_cast<void*>(ptr), dims, strides, box, es, CU_TENSOR_MAP_INTERLEAVE_NONE, sw,
           CU_TENSOR_MAP_L2_PROMOTION_L2_128B, CU_TENSOR_MAP_FLOAT_OOB_FILL_NONE);
        return;
    }
    if (hi) {
        cuuint64_t dims[3] = {cols, rows, hi == 64 ? 32u : 2u}; cuuint64_t strides[2] = {pitch * 2, hi * 2};
        cuuint32_t box[3] = {bc, br, bh}; cuuint32_t es[3] = {1, 1, 1};
        fn(tm, CU_TENSOR_MAP_DATA_TYPE_BFLOAT16, 3, const_cast<void*>(ptr), dims, strides, box, es, CU_TENSOR_MAP_INTERLEAVE_NONE, sw,
           CU_TENSOR_MAP_L2_PROMOTION_L2_128B, CU_TENSOR_MAP_FLOAT_OOB_FILL_NONE);
        return;
    }
    cuuint64_t dims[2] = {cols, rows}; cuuint64_t strides[1] = {(pitch ? pitch : cols) * 2};
    cuuint32_t box[2] = {bc, br}; cuuint32_t es[2] = {1, 1};
    fn(tm, CU_TENSOR_MAP_DATA_TYPE_BFLOAT16, 2, const_cast<void*>(ptr), dims, strides, box, es, CU_TENSOR_MAP_INTERLEAVE_NONE, sw,
       CU_TENSOR_MAP_L2_PROMOTION_L2_128B, CU_TENSOR_MAP_FLOAT_OOB_FILL_NONE);
}
template <typename... Args>
static void launch_pdl(void (*kern)(Args...), int grid, int block, int smem, Args... args) {
    cudaLaunchConfig_t cfg = {};
    cfg.gridDim = dim3(grid); cfg.blockDim = dim3(block); cfg.dynamicSmemBytes = smem; cfg.stream = cudaStreamPerThread;
    cudaLaunchAttribute at[1];
    at[0].id = cudaLaunchAttributeProgrammaticStreamSerialization; at[0].val.programmaticStreamSerializationAllowed = 1;
    cfg.attrs = at; cfg.numAttrs = 1;
    cudaLaunchKernelEx(&cfg, kern, args...);
}
static void launch_stage(int k, void* const* d_in, void* d_out) {
    const Par par = {k > 1 ? nullptr : (const bf16*)d_in[4], (const bf16*)d_in[5], (const bf16*)d_in[6], (const bf16*)d_in[7], (const bf16*)d_in[8], (const bf16*)d_in[9], k > 1, 0, (const bf16*)d_in[0],
                     (uint4*)h_sym[4], (uint4*)h_sym[2], (uint4*)h_sym[6], (uint4*)h_sym[3], (uint4*)h_sym[0], (float*)h_sym[5], (uint4*)h_sym[1], (const bf16*)d_in[1], (const bf16*)d_in[2]};
    auto a1 = h_nsm == 132 ? a1_kernel<true> : a1_kernel<false>;
    switch (k) {
        case 1: a1<<<h_nsm, A1_THREADS, A1_SMEM, cudaStreamPerThread>>>(par, h_tmX0, h_tmR0, h_tmX1st, h_tmW, h_tab[0]); break;
        case 3: launch_pdl(conv_kernel, DM / CV_CPB, CV_THREADS, CV_SMEM, 0, (const uint4*)h_sym[7], (const float4*)h_sym[4], (const bf16*)h_sym[8], (bf16*)h_sym[9], (const uint4*)h_sym[0], h_tmOut); break;
        case 5: launch_pdl(a1, h_nsm, A1_THREADS, A1_SMEM, par, h_tmX1, h_tmR1, h_tmX1st, h_tmW, h_tab[1]); break;
        case 7: launch_pdl(conv_kernel, DM / CV_CPB, CV_THREADS, CV_SMEM, 1, (const uint4*)h_sym[7] + SEQ / 8, (const float4*)h_sym[4] + SEQ / 2, (const bf16*)h_sym[8], (bf16*)h_sym[10], (const uint4*)h_sym[0], h_tmOut); break;
        default: break;
    }
}
static int n_stage_kernels() { return 9; }
static const char* stage_name(int k) { const char* n[] = {"kgen", "a1", "a2", "conv", "tr", "a1", "a2", "conv", "tr"}; return n[k]; }

extern "C" void kernel_launch(void* const* d_in, const int* in_sizes, int n_in, void* d_out, int out_size) {
    (void)in_sizes; (void)n_in; (void)out_size;
    static const void *p_in = nullptr, *p_w1 = nullptr, *p_w2 = nullptr, *p_out = nullptr;
    if (p_in != d_in[0] || p_w1 != d_in[1] || p_w2 != d_in[2] || p_out != d_out) {
        cudaFuncSetAttribute(conv_kernel, cudaFuncAttributeMaxDynamicSharedMemorySize, CV_SMEM);
        cudaFuncSetAttribute(a1_kernel<true>, cudaFuncAttributeMaxDynamicSharedMemorySize, A1_SMEM);
        cudaFuncSetAttribute(a1_kernel<false>, cudaFuncAttributeMaxDynamicSharedMemorySize, A1_SMEM);
        int dev; cudaGetDevice(&dev); cudaDeviceGetAttribute(&h_nsm, cudaDevAttrMultiProcessorCount, dev);
        if (h_nsm != 132) h_nsm = 128;
        cudaGetSymbolAddress(&h_sym[0], g_tap); cudaGetSymbolAddress(&h_sym[1], g_wq); cudaGetSymbolAddress(&h_sym[2], g_wo);
        cudaGetSymbolAddress(&h_sym[3], g_halo); cudaGetSymbolAddress(&h_sym[4], g_sum); cudaGetSymbolAddress(&h_sym[5], g_csp); cudaGetSymbolAddress(&h_sym[6], g_of);
        cudaGetSymbolAddress(&h_sym[7], g_piv); cudaGetSymbolAddress(&h_sym[8], g_x1T); cudaGetSymbolAddress(&h_sym[9], g_xcT); cudaGetSymbolAddress(&h_sym[10], g_yT);
        for (int i = 0; i < 264; i++) {
            const int s = i % 132, h = (s - 64) >> 1;
            const int t = h_nsm != 132 ? s : s < 64 ? ((s >> 1) & 7) * 16 + (s >> 4) * 2 + (s & 1) : s < 120 ? (1 + h % 7) * 16 + 8 + (h / 7) * 2 + (s & 1) : s < 124 ? 128 : s - 116;
            const int hg = (4 * (t >> 6) + (t & 3)) & 7;
            const uint64_t wp = (uint64_t)h_sym[1] + hg * 10 * WQ_STAGE;
            h_tab[i / 132].e[s] = make_uint4((uint32_t)wp, (uint32_t)(wp >> 32), ((t >> 2) & 15) | (i / 132) << 4 | hg << 8 | 5 * (hg >> 2) << 16 | (uint32_t)t << 24, 0);
        }
        void *px1, *px2;
        cudaGetSymbolAddress(&px1, g_x1T); cudaGetSymbolAddress(&px2, g_xcT);
        make_tmap(&h_tmX0, d_in[0], 128 * 640, 64, 64, 64, CU_TENSOR_MAP_SWIZZLE_128B, 1280, 640, 0);
        make_tmap(&h_tmX1, px2, 128, 64 * XCP, 64, 64, CU_TENSOR_MAP_SWIZZLE_128B, XCP, 64, 0);
        make_tmap(&h_tmR0, d_in[0], 640, 1024, 80, 64, CU_TENSOR_MAP_SWIZZLE_NONE, 1280, 640, 1);
        make_tmap(&h_tmR1, px2, 64, 640, 64, 80, CU_TENSOR_MAP_SWIZZLE_128B, XCP, 64, 1);
        make_tmap(&h_tmX1st, px1, 2048, 640, 64, 80, CU_TENSOR_MAP_SWIZZLE_128B, XCP);
        make_tmap(&h_tmW.q, d_in[1], 16, 640, 16, 32, CU_TENSOR_MAP_SWIZZLE_32B, 1920, 16, 5);
        make_tmap(&h_tmW.o, d_in[2], 640, 640, 4, 0, CU_TENSOR_MAP_SWIZZLE_32B);
        make_tmap(&h_tmW.t, d_in[2], 640, 640, 2, 0, CU_TENSOR_MAP_SWIZZLE_32B);
        make_tmap(&h_tmOut, d_out, 640, 1024, 80, 8, CU_TENSOR_MAP_SWIZZLE_NONE, 1280, 640, 1);
        p_in = d_in[0]; p_w1 = d_in[1]; p_w2 = d_in[2]; p_out = d_out;
    }
    for (int k = 0; k < n_stage_kernels(); k++) launch_stage(k, d_in, d_out);
}
```

```cpp
#include <cuda_runtime.h>
#include <cuda_bf16.h>
#include <cuda_fp16.h>
#include <stdint.h>
#include <cuda.h>

typedef __nv_bfloat16 bf16;

constexpr int SEQ = 2048;
constexpr int DM = 640;
constexpr int NMODE = 192;

__device__ __forceinline__ float bf2f(bf16 v) { return __bfloat162float(v); }
__device__ __forceinline__ float rbf(float v) {
    uint32_t r;
    asm("cvt.rn.bf16x2.f32 %0, %1, %2;" : "=r"(r) : "f"(v), "f"(0.f));
    return __uint_as_float(r);
}
__device__ __forceinline__ uint32_t pack2(float lo, float hi) {
    __nv_bfloat162 t = __floats2bfloat162_rn(lo, hi);
    return *reinterpret_cast<uint32_t*>(&t);
}
__device__ __forceinline__ void pdl_sync() {
    asm volatile("griddepcontrol.wait;" ::: "memory");
    asm volatile("griddepcontrol.launch_dependents;" ::: "memory");
}
__device__ __forceinline__ void pause(uint32_t n) { uint32_t c0, c1; asm volatile("mov.u32 %0, %clock;" : "=r"(c0) :: "memory"); do asm volatile("mov.u32 %0, %clock;" : "=r"(c1) :: "memory"); while (c1 - c0 < n); }
__device__ __forceinline__ float sqrt_apx(float v) { float r; asm("sqrt.approx.ftz.f32 %0, %1;" : "=f"(r) : "f"(v)); return r; }
__device__ __forceinline__ float rcp_apx(float v) { float r; asm("rcp.approx.ftz.f32 %0, %1;" : "=f"(r) : "f"(v)); return r; }
__device__ __forceinline__ uint32_t smem_u32(const void* p) { return (uint32_t)__cvta_generic_to_shared(p); }

constexpr int TAPB = 2944, TAPE = 928;
__device__ __align__(128) uint4 g_tap[DM * TAPB / 16];
#define XPAD 64
constexpr int XCP = SEQ + XPAD;
__device__ __align__(128) bf16 g_x1T[DM * XCP];
__device__ __align__(128) bf16 g_xcT[DM * XCP];
__device__ __align__(128) uint4 g_of[128 * 1280];
constexpr int WQ_STAGE = 240 * 128, WOB = 80 * 160;
__device__ __align__(128) uint4 g_wq[8 * 10 * WQ_STAGE / 16];
__device__ __align__(128) uint4 g_wo[64 * WOB / 16];
__device__ __align__(128) uint4 g_xb[128 * 240];
__device__ __align__(16) float g_csp[10 * 1920];
#define FSTR 32
__device__ __align__(128) float2 g_sum[2 * SEQ + 256 * FSTR];
__device__ __align__(16) bf16 g_piv[2 * SEQ];
__device__ __align__(128) bf16 g_yT[DM * XCP];
__device__ uint32_t g_epoch;
__device__ __align__(16) unsigned long long g_rstat[SEQ];
__device__ __align__(128) uint4 g_halo[640 * 148];
__device__ __forceinline__ unsigned long long tagw(uint32_t payload, uint32_t tag) { return ((unsigned long long)tag << 32) | payload; }
__device__ __forceinline__ ulonglong2 ld_tag2(const ulonglong2* p) {
    ulonglong2 v;
    asm volatile("ld.relaxed.gpu.global.v2.u64 {%0, %1}, [%2];" : "=l"(v.x), "=l"(v.y) : "l"(p) : "memory");
    return v;
}
__device__ __forceinline__ bool tag_ok(ulonglong2 v, uint32_t tag) { return (uint32_t)(v.x >> 32) == tag && (uint32_t)(v.y >> 32) == tag; }
__device__ __forceinline__ uint32_t ld_epoch() { uint32_t v; asm volatile("ld.relaxed.gpu.global.u32 %0, [%1];" : "=r"(v) : "l"(&g_epoch) : "memory"); return v + 1; }
constexpr int SPIN_MAX = 1 << 20;
__device__ __align__(128) uint32_t g_started[11 * 32];
__device__ __forceinline__ void sm_started(int slot) { asm volatile("red.relaxed.gpu.global.add.u32 [%0], 1;" ::"l"(g_started + slot) : "memory"); }
__device__ __forceinline__ void publish(int slot) {
    asm volatile("fence.proxy.async.global;" ::: "memory");
    asm volatile("red.release.gpu.global.add.u32 [%0], 1;" ::"l"(g_started + slot) : "memory");
}
__device__ __forceinline__ void await_all(int slot, uint32_t want) {
#pragma unroll 1
    for (int it = 0; it < SPIN_MAX; it++) {
        uint32_t v;
        asm volatile("ld.acquire.gpu.global.u32 %0, [%1];" : "=r"(v) : "l"(g_started + slot) : "memory");
        if (__all_sync(~0u, (int)(v - want) >= 0)) break;
        __nanosleep(50);
    }
    asm volatile("fence.proxy.async.global;" ::: "memory");
}
__device__ __noinline__ void sm_idle(int slot) {
    if (threadIdx.x != 288) return;
    asm volatile("fence.acq_rel.gpu;" ::: "memory");
    asm volatile("fence.proxy.async.global;" ::: "memory");
    sm_started(slot);
    const uint32_t want = ld_epoch() * gridDim.x;
    pdl_sync();
#pragma unroll 1
    for (int it = 0; it < SPIN_MAX; it++) {
        uint32_t v;
        asm volatile("ld.relaxed.gpu.global.u32 %0, [%1];" : "=r"(v) : "l"(g_started + slot) : "memory");
        if ((int)(v - want) >= 0) break;
        __nanosleep(100);
    }
}
struct TileTab { uint4 e[132]; };
__device__ __forceinline__ bool elect() {
    uint32_t p;
    asm volatile("{\n.reg .pred p;\nelect.sync _|p, 0xffffffff;\nselp.b32 %0, 1, 0, p;\n}" : "=r"(p));
    return p;
}
#define DBG_SYMS
#define TSTAMP(i)
#define TSTAMP1(i)
#define TSTAMP1T(i, t)
#define TSTAMP1X(i, t)
#define SPAN(k, i)
#define GSTAMP(arr, i)
#define TSTAMP2(i)
#define TSTAMP3(i)
#define TSTAMP4(i)
#define TSTAMPK(i, t)
#define TSTAMPC(i)
#define DBGC(i)
#define DBGV(i, v)
#define DBGCAL(i)

#define CSK(i)
#define CSK_END
#define CSA(i)
#define CSA_END
#define CST(i)
#define CST_END
#define CST_EXTRA 0
__device__ __forceinline__ void mma_bf16(float* d, uint32_t a0, uint32_t a1, uint32_t a2, uint32_t a3, uint32_t b0, uint32_t b1) {
    asm volatile("mma.sync.aligned.m16n8k16.row.col.f32.bf16.bf16.f32 {%0,%1,%2,%3}, {%4,%5,%6,%7}, {%8,%9}, {%0,%1,%2,%3};"
                 : "+f"(d[0]), "+f"(d[1]), "+f"(d[2]), "+f"(d[3]) : "r"(a0), "r"(a1), "r"(a2), "r"(a3), "r"(b0), "r"(b1));
}
__device__ __forceinline__ void mma_bf16_k8(float* d, uint32_t a0, uint32_t a1, uint32_t b0) {
    asm volatile("mma.sync.aligned.m16n8k8.row.col.f32.bf16.bf16.f32 {%0,%1,%2,%3}, {%4,%5}, {%6}, {%0,%1,%2,%3};"
                 : "+f"(d[0]), "+f"(d[1]), "+f"(d[2]), "+f"(d[3]) : "r"(a0), "r"(a1), "r"(b0));
}
__device__ __forceinline__ void ldsm_x4(uint32_t* r, uint32_t addr) {
    asm volatile("ldmatrix.sync.aligned.m8n8.x4.shared.b16 {%0,%1,%2,%3}, [%4];"
                 : "=r"(r[0]), "=r"(r[1]), "=r"(r[2]), "=r"(r[3]) : "r"(addr));
}

__device__ __forceinline__ void ldsm_x4_t(uint32_t* r, uint32_t addr) {
    asm volatile("ldmatrix.sync.aligned.m8n8.x4.trans.shared.b16 {%0,%1,%2,%3}, [%4];"
                 : "=r"(r[0]), "=r"(r[1]), "=r"(r[2]), "=r"(r[3]) : "r"(addr));
}
__device__ __forceinline__ void mbar_init(uint32_t bar, int count) { asm volatile("mbarrier.init.shared::cta.b64 [%0], %1;" ::"r"(bar), "r"(count)); }
__device__ __forceinline__ void mbar_arrive(uint32_t bar) { asm volatile("mbarrier.arrive.shared::cta.b64 _, [%0];" ::"r"(bar) : "memory"); }
__device__ __forceinline__ void mbar_wait(uint32_t bar, uint32_t parity) {
    asm volatile("{\n.reg .pred p;\nWAIT_LOOP:\n"
                 "mbarrier.try_wait.parity.shared::cta.b64 p, [%0], %1;\n"
                 "@p bra.uni WAIT_DONE;\nbra.uni WAIT_LOOP;\nWAIT_DONE:\n}" ::"r"(bar), "r"(parity) : "memory");
}

__device__ __forceinline__ void mbar_expect_tx(uint32_t bar, uint32_t bytes) {
    asm volatile("mbarrier.arrive.expect_tx.shared::cta.b64 _, [%0], %1;" ::"r"(bar), "r"(bytes) : "memory");
}
__device__ __forceinline__ void tma_load_2d(uint32_t dst, const void* tmap, int c0, int c1, uint32_t bar) {
    asm volatile("cp.async.bulk.tensor.2d.shared::cluster.global.mbarrier::complete_tx::bytes [%0], [%1, {%3, %4}], [%2];"
                 ::"r"(dst), "l"(tmap), "r"(bar), "r"(c0), "r"(c1) : "memory");
}
__device__ __forceinline__ void tma_load_3d(uint32_t dst, const void* tmap, int c0, int c1, int c2, uint32_t bar) {
    asm volatile("cp.async.bulk.tensor.3d.shared::cluster.global.mbarrier::complete_tx::bytes [%0], [%1, {%3, %4, %5}], [%2];"
                 ::"r"(dst), "l"(tmap), "r"(bar), "r"(c0), "r"(c1), "r"(c2) : "memory");
}
__device__ __forceinline__ void fence_async_smem() { asm volatile("fence.proxy.async.shared::cta;" ::: "memory"); }
__device__ __forceinline__ void bulk_load(uint32_t dst, const void* src, uint32_t bytes, uint32_t bar) {
    asm volatile("cp.async.bulk.shared::cluster.global.mbarrier::complete_tx::bytes [%0], [%1], %2, [%3];"
                 ::"r"(dst), "l"(src), "r"(bytes), "r"(bar) : "memory");
}
__device__ __forceinline__ void stsm_x4(uint32_t addr, uint32_t r0, uint32_t r1, uint32_t r2, uint32_t r3) {
    asm volatile("stmatrix.sync.aligned.m8n8.x4.shared.b16 [%0], {%1,%2,%3,%4};" ::"r"(addr), "r"(r0), "r"(r1), "r"(r2), "r"(r3) : "memory");
}
__device__ __forceinline__ void stsm_x4_t(uint32_t addr, uint32_t r0, uint32_t r1, uint32_t r2, uint32_t r3) {
    asm volatile("stmatrix.sync.aligned.m8n8.x4.trans.shared.b16 [%0], {%1,%2,%3,%4};" ::"r"(addr), "r"(r0), "r"(r1), "r"(r2), "r"(r3) : "memory");
}
__device__ __forceinline__ void prefetch_tmap(const void* tmap) { asm volatile("prefetch.tensormap [%0];" ::"l"(tmap) : "memory"); }

__device__ __forceinline__ float2 cexp_at(float wr2, float wi, float p) {
    float er;
    asm("ex2.approx.ftz.f32 %0, %1;" : "=f"(er) : "f"(wr2 * p));
    float th = wi * p;
    const float k = rintf(th * 0.15915494309189535f);
    th = fmaf(k, -6.2831854820251465f, th);
    th = fmaf(k, 1.7484555314695172e-7f, th);
    return make_float2(er * __cosf(th), er * __sinf(th));
}
__device__ __forceinline__ float2 cmul(float2 a, float2 b) {
    return make_float2(fmaf(a.x, b.x, -a.y * b.y), fmaf(a.x, b.y, a.y * b.x));
}
__device__ __forceinline__ float2 csqr(float2 a) { return make_float2(fmaf(a.x, a.x, -a.y * a.y), (a.x + a.x) * a.y); }
__device__ __forceinline__ uint32_t packh(float2 v) {
    uint32_t r;
    asm("cvt.rn.f16x2.f32 %0, %1, %2;" : "=r"(r) : "f"(v.y), "f"(v.x));
    return r;
}
__device__ __forceinline__ uint2 packr(float2 v) { return make_uint2(packh(v), packh(make_float2(-v.y, v.x))); }
__device__ __forceinline__ uint32_t hcmul(uint32_t a, uint2 b) {
    const __half2 x = *reinterpret_cast<const __half2*>(&a);
    const __half2 r = __hfma2(__high2half2(x), *reinterpret_cast<const __half2*>(&b.y), __hmul2(__low2half2(x), *reinterpret_cast<const __half2*>(&b.x)));
    return *reinterpret_cast<const uint32_t*>(&r);
}

struct Par { const bf16 *logA, *Aim, *Cre, *Cim, *logdt, *dsk; int layer, pad; const bf16* x; uint4 *sum, *wop, *of, *halo, *tap; float* csp; uint4* wq; const bf16 *wqkv, *wo; };
struct KgMaps { CUtensorMap q, o, t; };

__device__ __forceinline__ void bulk_prefetch(const void* p, uint32_t bytes) { asm volatile("cp.async.bulk.prefetch.L2.global [%0], %1;" ::"l"(p), "r"(bytes) : "memory"); }
__device__ __forceinline__ void bulk_store(void* dst, uint32_t src, uint32_t bytes) { asm volatile("cp.async.bulk.global.shared::cta.bulk_group [%0], [%1], %2;" ::"l"(dst), "r"(src), "r"(bytes) : "memory"); }
__device__ __forceinline__ void kgen_first(const Par& in, const KgMaps& tm, const uint32_t b0, const uint32_t wbar, const bool one) {
    const uint32_t blk = blockIdx.x, sec = (blk >= 40) + (blk >= 80), it = (blk >> 3) - 5 * sec, up = (blk >> 2) & 1, hi = blk >> 6;
    auto fetch = [&](int h) {
        if (blk < 120) asm volatile("cp.async.bulk.tensor.4d.shared::cluster.global.mbarrier::complete_tx::bytes [%0], [%1, {%3, %3, %4, %5}], [%2];"
                                    ::"r"(b0 + 10240 * h), "l"(&tm.q), "r"(wbar + 8 * h), "r"(0), "r"(sec * 40 + (blk & 7) * 5), "r"(2 * it + 10 * (up ^ h)) : "memory");
    };
    auto fetch_o = [&](int i) {
        asm volatile("cp.async.bulk.tensor.5d.shared::cluster.global.mbarrier::complete_tx::bytes [%0], [%1, {%3, %3, %4, %3, %5}], [%2];"
                     ::"r"(b0 + 20480 + i * 5120), "l"(&tm.o + i), "r"(wbar + 16), "r"(0), "r"((blk & 7) * 10 + (hi + i) * 4), "r"(((blk >> 3) & 7) * 5) : "memory");
    };
    if (one) {
#pragma unroll
        for (int i = 0; i < 3; i++) mbar_init(wbar + 8 * i, 1);
        asm volatile("fence.mbarrier_init.release.cluster;" ::: "memory");
        fetch(0);
    }
    __syncwarp();
    if (blk >> 20) __trap();
    if (one) {
        bulk_prefetch(in.wqkv + blk * 9600, 19200);
        fetch(1);
        bulk_prefetch(in.wo + blk * 3200, 6400);
        fetch_o(0);
        if (hi) fetch_o(1);
        mbar_expect_tx(wbar, 10240); mbar_expect_tx(wbar + 8, 10240); mbar_expect_tx(wbar + 16, 5120 + hi * 2560);
        bulk_prefetch(in.x + blk * 10240, 20480);
    }
}
__device__ __forceinline__ void kgen_side(const Par& in, const uint32_t b0, const uint32_t wbar) {
    const uint32_t blk = blockIdx.x, sec = (blk >= 40) + (blk >= 80), it = (blk >> 3) - 5 * sec, cg = (blk >> 3) & 7, hb = blk & 7;
    unsigned char* dst = reinterpret_cast<unsigned char*>(in.wq) + (hb * 10 + it) * WQ_STAGE + sec * 5120;
    if (blk < 120) {
        mbar_wait(wbar, 0);
        CSK(2);
        bulk_store(dst, b0, 5120); bulk_store(dst + 15360, b0 + 5120, 5120);
        mbar_wait(wbar + 8, 0);
        CSK(3);
        bulk_store(dst + 5 * WQ_STAGE, b0 + 10240, 5120); bulk_store(dst + 5 * WQ_STAGE + 15360, b0 + 15360, 5120);
        asm volatile("cp.async.bulk.commit_group;" ::: "memory");
        asm volatile("cp.async.bulk.wait_group 0;" ::: "memory");
        CSK(4);
        publish(96 + 32 * hb);
        CSK(5);
    }
    if (blk < 128) {
        mbar_wait(wbar + 16, 0);
        bulk_store(reinterpret_cast<unsigned char*>(in.wop) + (cg * 8 + (hb == cg ? 0 : hb + (hb < cg))) * WOB + (blk >> 6) * 5120, b0 + 20480, blk < 64 ? 5120 : 7680);
        asm volatile("cp.async.bulk.commit_group;" ::: "memory");
    }
}
__device__ __forceinline__ void kgen_sums(const Par& in, const uint32_t b0, const int h) {
    const int lane = threadIdx.x & 31, blk = blockIdx.x;
    if (blk < 120) {
        float cs[5][4] = {};
#pragma unroll
        for (int a = 0; a < 4; a++)
#pragma unroll
            for (int j = 0; j < 5; j++) {
                uint32_t w[4];
                ldsm_x4_t(w, b0 + h * 10240 + j * 1024 + ((lane >> 4) * 8 + (lane & 7)) * 32 + ((((lane >> 3) ^ (lane >> 2)) & 1) << 4) + (a >> 1) * 5120 + (a & 1) * 512);
                mma_bf16(cs[j], w[0], w[1], w[2], w[3], 0x3f803f80u, 0x3f803f80u);
            }
#pragma unroll
        for (int j = 0; j < 5; j++)
            if ((lane & 3) < 2) in.csp[(blk + 120 * h) * 80 + j * 16 + (lane >> 2) + 8 * (lane & 3)] = (lane & 3) ? cs[j][2] : cs[j][0];
    }
}
struct KgPar { uint32_t pw[4], ph[4], pdt, pdsk; };
__device__ __forceinline__ void kgen_load(const Par& in, const bf16* logA, const int w11, KgPar& k) {
    const uint32_t o = blockIdx.x * 480 + min(w11 * 48, w11 * 32 + 128), ow = o + (threadIdx.x & 31), oh = o + ow + (w11 < 8 ? 64 : 0);
    k.pdt = reinterpret_cast<const unsigned short*>(in.logdt)[ow / 96];
    k.pdsk = reinterpret_cast<const unsigned short*>(in.dsk)[ow / 96];
#pragma unroll
    for (int i = 0; i < 4; i++) {
        const bf16* p = i == 0 ? logA : i == 1 ? in.Aim : i == 2 ? in.Cre : in.Cim;
        k.pw[i] = reinterpret_cast<const uint32_t*>(p)[ow]; k.ph[i] = reinterpret_cast<const unsigned short*>(p)[oh];
    }
}
__device__ __forceinline__ void kgen_tables(const Par& in, uint4* tabs, const int w11, const KgPar& kp) {
    const int lane = threadIdx.x & 31, grp = min(w11 >> 1, 4), warp = w11 - 2 * grp;
    const int blk = blockIdx.x, d = blk * 5 + grp, tid = warp * 32 + lane;
    uint4* tab = tabs + grp * (2 * 256);
    const uint32_t *pw = kp.pw, *ph = kp.ph;
#pragma unroll
    for (int i = 0; i < 3; i++)
        if (i < 2 || w11 * 32 + lane < 36) asm volatile("st.global.v4.u32 [%0], {%1,%1,%1,%1};" ::"l"(in.halo + blk * 740 + w11 * 32 + lane + 352 * i), "r"(~0u));
    __syncwarp();
    if (w11 == 10) {
        if (lane < 16) in.sum[blk * 16 + lane] = make_uint4(0, 0, 0, 0);
        else if (lane < 20) reinterpret_cast<uint32_t*>(in.sum + 2048)[(blk * 4 + lane - 16) * FSTR] = 0;
    } else if (w11 > 1) asm volatile("bar.arrive 9, 352;" ::: "memory");
#pragma unroll
    for (int i = 0; i < 6; i++) tabs[w11 * 256 + 32 * i + lane] = make_uint4(0, 0, 0, 0);
    __syncwarp();
    CSK(1);
    const uint32_t tw = smem_u32(tabs) + w11 * 4096;
    const int g = lane >> 2, t = lane & 3;
    const int mt = lane >> 3, r = lane & 7;
    const uint32_t st1 = tw + mt * 1024 + r * 16, st2 = tw + (mt & 1) * 1024 + (mt >> 1) * 128 + ((r ^ (mt >> 1)) << 4), st3 = tw + 2048 + mt * 128 + ((r ^ mt) << 4);
    const uint32_t lda = tw + (mt & 1) * 1024 + r * 128 + (((mt >> 1) ^ r) << 4), ldb = tw + (mt >> 1) * 1024 + r * 128 + (((mt & 1) ^ r) << 4), ldc = tw + 2048 + r * 128 + ((mt ^ r) << 4);
    auto ldsm = [](uint32_t* v, uint32_t a) {
        asm volatile("ldmatrix.sync.aligned.m8n8.x4.shared.b16 {%0,%1,%2,%3}, [%4];" : "=r"(v[0]), "=r"(v[1]), "=r"(v[2]), "=r"(v[3]) : "r"(a) : "memory");
    };
    auto mma = [](float* c, const uint32_t* a, const uint32_t* b) {
        asm("mma.sync.aligned.m16n8k16.row.col.f32.f16.f16.f32 {%0,%1,%2,%3}, {%4,%5,%6,%7}, {%8,%9}, {%0,%1,%2,%3};"
            : "+f"(c[0]), "+f"(c[1]), "+f"(c[2]), "+f"(c[3]) : "r"(a[0]), "r"(a[1]), "r"(a[2]), "r"(a[3]), "r"(b[0]), "r"(b[1]));
    };
    asm volatile("st.shared.u32 [%0], %1;" ::"r"(tw + 3072), "r"(st1 ^ st2 ^ st3 ^ lda ^ ldb ^ ldc) : "memory");
    if (in.pad) __trap();
    const float dt = rbf(expf(__uint_as_float(kp.pdt << 16)));
    const uint32_t cm = __vmaxu2(__vmaxu2(pw[2] & 0x7fff7fffu, pw[3] & 0x7fff7fffu), __byte_perm(ph[2], ph[3], 0x5410) & 0x7fff7fffu);
    const int ex = min(max((int)(__float_as_uint(__uint_as_float(__reduce_max_sync(~0u, max(cm << 16, cm & 0xffff0000u))) * dt) >> 23), 20), 240);
    const float scale = __uint_as_float((uint32_t)(127 + 10 + 127 - ex) << 23), unscale = 2.0f * __uint_as_float((uint32_t)(ex - 10) << 23);
    float k2048 = 0.f;
    float acc[5][4] = {};
    uint32_t af[4][4] = {};
    auto rest = [&] {
        uint32_t b[4][4], c[8];
#pragma unroll
        for (int k = 0; k < 4; k++) {
            ldsm(b[k], ldb ^ (k << 5));
            if (!(k & 1)) ldsm(c + 2 * k, ldc ^ (k << 5));
        }
#pragma unroll
        for (int k = 0; k < 4; k++) { mma(acc[2], af[k], b[k]); mma(acc[3], af[k], b[k] + 2); mma(acc[4], af[k], c + 2 * k); }
    };
#pragma unroll 1
    for (uint32_t sel = 0x1076; sel < (grp < 4 ? 0x6000u : 0x4000u); sel += 0x2200) {
        rest();
        auto par = [&](int i) { return __uint_as_float(__byte_perm(pw[i], ph[i], sel)); };
        const float wr2 = -rbf(expf(par(0))) * dt * 1.4426950408889634f, wi = par(1) * dt;
        const float2 y1 = cexp_at(wr2, -wi, 1.f), w64 = cexp_at(wr2, wi, 64.f), y4 = csqr(csqr(y1)), z8 = csqr(make_float2(y4.x, -y4.y)), y128 = csqr(make_float2(w64.x, -w64.y));
        float2 h0 = make_float2(1.f, 0.f), g0 = make_float2(par(2) * dt * scale, -par(3) * dt * scale);
        const float2 v2 = csqr(y128), v3 = cmul(v2, y128), v4 = csqr(v2), v8 = csqr(v4), c8 = cmul(g0, v8);
        const uint2 z64 = packr(w64), v[8] = {make_uint2(packh(c8), 0u), packr(y128), packr(v2), packr(v3), packr(v4), packr(cmul(v4, y128)), packr(csqr(v3)), packr(cmul(v4, v3))};
        k2048 += fmaf(c8.x, v8.x, -c8.y * v8.y);
        uint32_t ge[4];
#pragma unroll
        for (int e = 0; e < 8; e++) {
            const uint32_t p = packh(h0), q = packh(g0);
            if (!(e & 1)) ge[e >> 1] = q;
            stsm_x4((st1 ^ (e << 4)) + e * 128, p, e ? hcmul(p, z64) : z64.x, q, hcmul(q, v[1]));
            if (e < 7) { h0 = e ? cmul(h0, z8) : z8; g0 = cmul(g0, y1); }
        }
        __syncwarp();
        uint32_t b[4][4];
#pragma unroll
        for (int k = 0; k < 4; k++) { ldsm(af[k], lda ^ (k << 5)); ldsm(b[k], (ldb ^ (k << 5)) + 2048); }
#pragma unroll
        for (int e = 0; e < 8; e += 2) {
            stsm_x4((st2 ^ (e << 4)) + e * 128, hcmul(ge[e & 3], v[2 + (e >> 2)]), hcmul(ge[0], v[4 + (e >> 1)]), hcmul(ge[(e & 3) + 1], v[2 + (e >> 2)]), hcmul(ge[2], v[4 + (e >> 1)]));
            if (!(e & 3)) stsm_x4((st3 ^ (e << 4)) + e * 128, e ? hcmul(v[0].x, v[e]) : v[0].x, hcmul(v[0].x, v[e + 1]), hcmul(v[0].x, v[e + 2]), hcmul(v[0].x, v[e + 3]));
            mma(acc[0], af[e >> 1], b[e >> 1]);
            mma(acc[1], af[e >> 1], b[e >> 1] + 2);
        }
        __syncwarp();
        if (sel == 0x1076) CSK(3);
    }
    rest();
#pragma unroll
    for (int e = 0; e < 5; e++) k2048 += __shfl_xor_sync(~0u, k2048, 1 << e);
    {
        float* Pp = reinterpret_cast<float*>(tab + warp * 256);
        auto sw = [](int i) { return i ^ ((i >> 2) & 24); };
#pragma unroll
        for (int h = 0; h < 2; h++) {
            const int b = g + 8 * h;
            *reinterpret_cast<float2*>(Pp + sw(8 * b + 2 * t)) = make_float2(acc[0][2 * h] * unscale, acc[0][2 * h + 1] * unscale);
            *reinterpret_cast<float2*>(Pp + 128 + sw(8 * b + 2 * t)) = make_float2(acc[1][2 * h] * unscale, acc[1][2 * h + 1] * unscale);
            *reinterpret_cast<float2*>(Pp + 256 + sw(4 * b + 2 * (t & 1) + 64 * (t >> 1))) = make_float2(acc[2][2 * h] * unscale, acc[2][2 * h + 1] * unscale);
            *reinterpret_cast<float2*>(Pp + 384 + sw(2 * b + 32 * t)) = make_float2(acc[3][2 * h] * unscale, acc[3][2 * h + 1] * unscale);
            Pp[512 + sw(b + 32 * t)] = acc[4][2 * h] * unscale;
            Pp[512 + sw(b + 32 * t + 16)] = acc[4][2 * h + 1] * unscale;
        }
        if (lane == 0) Pp[640] = k2048 * unscale;
    }
    CSK(4);
    asm volatile("bar.sync %0, %1;" ::"r"(grp + 4), "r"(grp < 4 ? 64 : 96) : "memory");
    if (warp == 2) return;
    const float* Kp = reinterpret_cast<const float*>(tab);
    auto ksum = [&](int i) -> float { return rbf(Kp[i] + Kp[1024 + i] + (grp < 4 ? 0.f : Kp[2048 + i])); };
    auto ksum2 = [&](int q) -> float2 {
        q ^= (q >> 2) & 12;
        const float2 a = reinterpret_cast<const float2*>(Kp)[q], b = reinterpret_cast<const float2*>(Kp)[512 + q];
        const float2 c = grp < 4 ? make_float2(0.f, 0.f) : reinterpret_cast<const float2*>(Kp)[1024 + q];
        return make_float2(a.x + b.x + c.x, a.y + b.y + c.y);
    };
    {
        uint2* W2 = reinterpret_cast<uint2*>(in.tap + d * (TAPB / 16)) + 8;
        uint2* E4 = W2 + (TAPE - 64) / 8;
        float2 v = ksum2(64 * warp + lane), z = ksum2(64 * warp + 32 + lane), y = ksum2(128 + tid);
        const int q = (96 + tid) ^ (((96 + tid) >> 2) & 6);
        const float4 ua = reinterpret_cast<const float4*>(Kp)[q], uc = reinterpret_cast<const float4*>(Kp)[256 + q], ud = grp < 4 ? make_float4(0.f, 0.f, 0.f, 0.f) : reinterpret_cast<const float4*>(Kp)[512 + q];
        const float4 ub = make_float4(uc.x + ud.x, uc.y + ud.y, uc.z + ud.z, uc.w + ud.w);
        const float s1 = ksum(tid == 31 ? 336 : lane ? 384 : 103), s2 = ksum(tid == 31 ? 512 : tid ? 640 : 231);
        if (tid == 0) v.x += __uint_as_float(kp.pdsk << 16);
        if (tid == 63) y.y -= s1;
        const uint32_t lo = pack2(v.x, v.y), hi = pack2(z.x, z.y), tp = pack2(y.x, y.y);
        uint32_t nl = __shfl_sync(~0u, lo, lane - 1), nh = __shfl_sync(~0u, lane == 31 ? lo : hi, lane - 1), nt = __shfl_sync(~0u, tp, lane + 1);
        if (lane == 0) nl = warp ? __float_as_uint(s1) : 0u;
        if (lane == 31) nt = warp ? 0u : __float_as_uint(s1) >> 16;
        W2[64 * warp + lane] = make_uint2(__byte_perm(lo, nl, 0x7610), __byte_perm(lo, 0, 0x1032));
        W2[64 * warp + lane + 32] = make_uint2(__byte_perm(hi, nh, 0x7610), __byte_perm(hi, 0, 0x1032));
        reinterpret_cast<uint4*>(W2)[64 + tid] = make_uint4(__byte_perm(tp, __float_as_uint(s2), tid ? 0x1010 : 0x7610), __byte_perm(tp, 0, 0x1010), __byte_perm(tp, 0, 0x1032), __byte_perm(nt, tp, 0x7610));
        E4[(tid < 32 ? 159 : 209 - 32) + tid] = make_uint2(pack2(ua.x + ub.x, ua.y + ub.y), pack2(ua.z + ub.z, ua.w + ub.w - (tid == 31 ? s2 : 0.f)));
        if (tid == 63) E4[241] = make_uint2(__float_as_uint(s2) >> 16, 0u);
    }
    CSK(5);
    SPAN(0, 3);
}

#define CV_SLEEP 40
#define CV_TD1 500
#define CV_TD0 0
#define CV_LD "ld.relaxed.gpu.global"
#define CV_NL 1
#define CV_D2 3
#define CV_PDH 12
#define CV_PDF 4
#define CV_HAND 7
constexpr int CV_CPB = 5;
constexpr int CV_THREADS = 512;
constexpr int UPADF = 128;
constexpr int ULEN = UPADF + SEQ;
constexpr int XLEN = XCP;
constexpr int BX_5 = 0, BX_3 = 3264, BX_9 = 6528, BX_7 = 8960, BX_LEN = 11392;
constexpr int CV_SM_U = 0;
constexpr int CV_SM_T = CV_CPB * ULEN * 2;
constexpr int CV_SM_B = CV_SM_T + CV_CPB * TAPB;
constexpr int CV_SM_X = CV_SM_B + CV_CPB * BX_LEN;
constexpr int CV_SM_Y = (CV_SM_X + CV_CPB * XLEN * 2 + 127) & ~127;
constexpr int CV_SM_CNT = CV_SM_Y + CV_CPB * 8192;
constexpr int CV_SM_O = CV_SM_CNT + 128;
constexpr int CV_SMEM = CV_SM_O + 20480 + CST_EXTRA;
static_assert(ULEN % 128 == 0 && CV_SM_B % 128 == 0 && CV_SM_CNT % 128 == 0, "layout");

__device__ __forceinline__ uint32_t sub2(uint32_t x, uint32_t m) {
    const __nv_bfloat162 d = __hsub2(*reinterpret_cast<const __nv_bfloat162*>(&x), *reinterpret_cast<const __nv_bfloat162*>(&m));
    return *reinterpret_cast<const uint32_t*>(&d);
}
__device__ __forceinline__ uint32_t add2(uint32_t x, uint32_t y) {
    const __nv_bfloat162 d = __hadd2_rn(*reinterpret_cast<const __nv_bfloat162*>(&x), *reinterpret_cast<const __nv_bfloat162*>(&y));
    return *reinterpret_cast<const uint32_t*>(&d);
}
__device__ __forceinline__ void wgmma_fence() { asm volatile("wgmma.fence.sync.aligned;" ::: "memory"); }
__device__ __forceinline__ void wgmma_commit() { asm volatile("wgmma.commit_group.sync.aligned;" ::: "memory"); }
template <int N> __device__ __forceinline__ void wgmma_wait() { asm volatile("wgmma.wait_group.sync.aligned %0;" ::"n"(N) : "memory"); }
__device__ __forceinline__ uint64_t make_desc(uint32_t addr, uint32_t lbo, uint32_t sbo, uint32_t mode) {
    return (uint64_t)((addr & 0x3FFFF) >> 4) | ((uint64_t)(lbo >> 4) << 16) | ((uint64_t)(sbo >> 4) << 32) | ((uint64_t)mode << 62);
}
__device__ __forceinline__ void wgmma_rs128(float (&d)[64], uint2 hi, uint2 lo, uint64_t db, int acc) {
    asm volatile("{\n.reg .pred p;\nsetp.ne.b32 p, %69, 0;\nwgmma.mma_async.sync.aligned.m64n128k16.f32.bf16.bf16 {%0,%1,%2,%3,%4,%5,%6,%7,%8,%9,%10,%11,%12,%13,%14,%15,%16,%17,%18,%19,%20,%21,%22,%23,%24,%25,%26,%27,%28,%29,%30,%31,%32,%33,%34,%35,%36,%37,%38,%39,%40,%41,%42,%43,%44,%45,%46,%47,%48,%49,%50,%51,%52,%53,%54,%55,%56,%57,%58,%59,%60,%61,%62,%63}, {%64,%65,%66,%67}, %68, p, 1, 1, 0;\n}"
                 : "+f"(d[0]), "+f"(d[1]), "+f"(d[2]), "+f"(d[3]), "+f"(d[4]), "+f"(d[5]), "+f"(d[6]), "+f"(d[7]), "+f"(d[8]), "+f"(d[9]), "+f"(d[10]), "+f"(d[11]), "+f"(d[12]), "+f"(d[13]), "+f"(d[14]), "+f"(d[15]), "+f"(d[16]), "+f"(d[17]), "+f"(d[18]), "+f"(d[19]), "+f"(d[20]), "+f"(d[21]), "+f"(d[22]), "+f"(d[23]), "+f"(d[24]), "+f"(d[25]), "+f"(d[26]), "+f"(d[27]), "+f"(d[28]), "+f"(d[29]), "+f"(d[30]), "+f"(d[31]), "+f"(d[32]), "+f"(d[33]), "+f"(d[34]), "+f"(d[35]), "+f"(d[36]), "+f"(d[37]), "+f"(d[38]), "+f"(d[39]), "+f"(d[40]), "+f"(d[41]), "+f"(d[42]), "+f"(d[43]), "+f"(d[44]), "+f"(d[45]), "+f"(d[46]), "+f"(d[47]), "+f"(d[48]), "+f"(d[49]), "+f"(d[50]), "+f"(d[51]), "+f"(d[52]), "+f"(d[53]), "+f"(d[54]), "+f"(d[55]), "+f"(d[56]), "+f"(d[57]), "+f"(d[58]), "+f"(d[59]), "+f"(d[60]), "+f"(d[61]), "+f"(d[62]), "+f"(d[63])
                 : "r"(hi.x), "r"(hi.y), "r"(lo.x), "r"(lo.y), "l"(db), "r"(acc));
}
template <int V> struct Int { __device__ constexpr operator int() const { return V; } };
__device__ __forceinline__ void sts4(uint32_t a, const uint32_t* v) { asm volatile("st.shared.v4.u32 [%0], {%1,%2,%3,%4};" ::"r"(a), "r"(v[0]), "r"(v[1]), "r"(v[2]), "r"(v[3]) : "memory"); }
__device__ __forceinline__ uint32_t lds1(uint32_t a) { uint32_t v; asm volatile("ld.shared.u32 %0, [%1];" : "=r"(v) : "r"(a) : "memory"); return v; }
__device__ __forceinline__ uint32_t lds1v(uint32_t a) { uint32_t v; asm volatile("ld.volatile.shared.u32 %0, [%1];" : "=r"(v) : "r"(a) : "memory"); return v; }
__device__ __forceinline__ uint4 lds4(uint32_t a) { uint4 v; asm volatile("ld.shared.v4.u32 {%0,%1,%2,%3}, [%4];" : "=r"(v.x), "=r"(v.y), "=r"(v.z), "=r"(v.w) : "r"(a) : "memory"); return v; }
__device__ __forceinline__ uint4 ldx(uint32_t a) {
    uint4 v;
    asm volatile("ld.shared.v2.u32 {%0,%1}, [%4];\nld.shared.v2.u32 {%2,%3}, [%4+128];" : "=r"(v.x), "=r"(v.y), "=r"(v.z), "=r"(v.w) : "r"(a) : "memory");
    return v;
}
__device__ __forceinline__ void cv_store(unsigned char* p, uint4 x, uint4 y) {
    asm volatile("st.relaxed.gpu.global.v2.u32 [%0], {%1,%2};" ::"l"(p), "r"(add2(x.x, __byte_perm(y.x, y.y, 0x5410))), "r"(add2(x.y, __byte_perm(y.z, y.w, 0x5410))) : "memory");
    asm volatile("st.relaxed.gpu.global.v2.u32 [%0], {%1,%2};" ::"l"(p + 128), "r"(add2(x.z, __byte_perm(y.x, y.y, 0x7632))), "r"(add2(x.w, __byte_perm(y.z, y.w, 0x7632))) : "memory");
}
__device__ __forceinline__ int usw(int ch) { return ch ^ ((ch >> 3) & 1); }
__global__ void __launch_bounds__(CV_THREADS, 1) conv_kernel(int layer, const uint4* __restrict__ piv, const float4* __restrict__ sum, const bf16* __restrict__ x1T,
                                                             bf16* __restrict__ dst, const uint4* __restrict__ tap, const __grid_constant__ CUtensorMap tmOut) {
    extern __shared__ __align__(1024) unsigned char sm[];
    SPAN(3 + 4 * layer, 0);
    bf16* Us = reinterpret_cast<bf16*>(sm + CV_SM_U);
    bf16* Xs = reinterpret_cast<bf16*>(sm + CV_SM_X);
#define CV_IDX int tid; asm volatile("mov.u32 %0, %tid.x;" : "=r"(tid)); const int lane = tid & 31, warp = __shfl_sync(~0u, tid >> 5, 0);
    const int d0 = blockIdx.x * CV_CPB, tile = blockIdx.x; (void)tile;
    const uint32_t cnt = smem_u32(sm + CV_SM_CNT);
    struct Lc { uint32_t a4, a8, uc, ud, y, e4, en, sp, ss; int go; };
    auto lane_consts = [&](int lane, int c) {
        const int mat = lane >> 3, r = lane & 7, g = lane >> 2, ti = lane & 3, e = g - 2 * ti;
        const int j2 = 13 + (r ^ 1) + 8 * (mat >> 1), j3 = j2 + 2, i0 = 8 * (mat & 1);
        const uint32_t sb = smem_u32(sm), oc = sb + usw(16 * (mat >> 1) + 2 * r + (mat & 1)) * 16;
        const Lc l = {sb + CV_SM_B + c * BX_LEN + ((j2 & 1) ? BX_3 + (4 * j2 + i0 + 84) * 2 : BX_5 + (4 * j2 + i0 + 80) * 2),
                      sb + CV_SM_B + c * BX_LEN + ((j3 & 1) ? BX_7 : BX_9) + (8 * j3 + i0 + 136) * 2,
                      oc + CV_SM_U + (c * ULEN + UPADF) * 2, sb + CV_SM_U + (c * ULEN + UPADF) * 2 + usw(16 * mat + 2 * r + 2) * 16, oc + CV_SM_Y + c * 8192,
                      sb + CV_SM_T + c * TAPB + TAPE + (307 + 2 * g - ti) * 4, sb + CV_SM_T + c * TAPB + (528 + e) * 4,
                      e == -5 ? 0x4410u : e == -4 ? 0x1044u : 0x4444u, e == 3 ? 0x4410u : e == 4 ? 0x1044u : 0x4444u,
                      c * XCP * 2 + (lane >> 4) * 256 + (lane & 15) * 8};
        asm volatile("st.shared.u32 [%0], %1;" ::"r"(sb + CV_SM_CNT + 120), "r"(l.y ^ l.a4 ^ l.a8 ^ l.uc ^ l.ud ^ l.e4 ^ l.en ^ l.sp ^ l.ss ^ l.go) : "memory");
        return l;
    };
    unsigned char* const dq = reinterpret_cast<unsigned char*>(dst + (size_t)d0 * XCP);
    auto far = [&](auto T0_, const auto& seq, const Lc& lc, int c, int lane, const uint2 (&f)[20], uint32_t kk) {
        constexpr int T0 = T0_, T1 = T0 + 6, TC = T0 > 7 ? T0 : 7, NS = sizeof(seq) / sizeof(seq[0]), PD = T0 > 7 ? CV_PDH : CV_PDF;
        uint32_t bq[28], yw[4], yz[4], P, S;
        uint4 xv, yv;
        asm("prmt.b32 %0, %1, 0, %2;" : "=r"(P) : "r"(kk), "r"(lc.sp));
        asm("prmt.b32 %0, %1, 0, %2;" : "=r"(S) : "r"(kk), "r"(lc.ss));
#pragma unroll
        for (int k = 0; 2 * k < T1 - TC + 4; k++) ldsm_x4(bq + 4 * k, lc.uc + (TC - 8) * 256 + 512 * k);
#pragma unroll
        for (int k = 0; 4 * k < T1 - TC; k++) ldsm_x4(bq + 20 + 4 * k, lc.ud + (TC - 8) * 256 + 1024 * k);
        CST(3);
        mbar_wait(cnt + 8 * c, 0);
        mbar_wait(cnt + 40, 0);
        CST(4);
        float acc[6][4] = {};
        uint32_t a[PD + 1][4];
#pragma unroll
        for (int i = -PD; i < NS + 3; i++) {
            if (i + PD < NS) ldsm_x4_t(a[(i + PD) % (PD + 1)], seq[i + PD] < 32 ? lc.a4 + (seq[i + PD] - 2) * 128 : lc.a8 + (seq[i + PD] - 34) * 256);
            if (i < 0) continue;
#pragma unroll
            for (int T = T0; T < T1; T++) {
                if (i >= NS) break;
                const int ee = seq[i] < 32 ? 2 * T - 6 - seq[i] : T + 35 - seq[i];
                if (i == 0 && T >= TC) mma_bf16(acc[T - T0], P, 0u, S, P, bq[2 * (T - TC)], bq[2 * (T - TC) + 1]);
                if (i == 1 && T >= TC) mma_bf16_k8(acc[T - T0], 0u, S, bq[20 + T - TC]);
                if (i == (T >= TC ? 2 : 0)) mma_bf16(acc[T - T0], f[19].x, 0u, f[19].y, f[19].x, bq[2 * (T - TC + 4)], bq[2 * (T - TC + 4) + 1]);
                if (seq[i] < 32 ? ee >= 0 && ee <= 9 : ee >= 10) mma_bf16(acc[T - T0], a[i % (PD + 1)][0], a[i % (PD + 1)][1], a[i % (PD + 1)][2], a[i % (PD + 1)][3], f[ee].x, f[ee].y);
            }
#pragma unroll
            for (int k = 0; k < 3; k++) {
                const int o = 256 * T0 + 512 * k;
                auto at = [&](int d) { return i - d >= 0 && i - d < NS && seq[i - d < 0 ? 0 : i - d < NS ? i - d : 0] == 2 * T0 + 4 * k - 4; };
                if (at(CV_D2)) {
                    cv_store(dq + lc.go + o, xv, yv);
                    if (layer > 19 - 2 * k) __trap();
                }
                if (at(-2)) { ldsm_x4_t(yw, lc.y + o); ldsm_x4_t(yz, lc.y + 3584 + o); }
                if (at(1)) {
#pragma unroll
                    for (int q = 0; q < 4; q++) yw[q] = add2(add2(yw[q], yz[q]), pack2(acc[2 * k + (q >> 1)][2 * (q & 1)], acc[2 * k + (q >> 1)][2 * (q & 1) + 1]));
                    stsm_x4_t(lc.y + o, yw[0], yw[1], yw[2], yw[3]);
                    xv = ldx(smem_u32(Xs) + lc.go + o);
                    __syncwarp();
                    yv = lds4(smem_u32(sm + CV_SM_Y) + c * 8192 + o + usw(lane) * 16);
                    if (layer > 20 - 2 * k) __trap();
                    if (k == 2) CST(6);
                }
            }
        }
    };
    TSTAMP1X(9, 256);
    if (threadIdx.x >= 256) {
        if (threadIdx.x < 288 && elect()) {
            mbar_init(cnt + 48, 1);
            asm volatile("fence.mbarrier_init.release.cluster;" ::: "memory");
            bulk_load(smem_u32(sm + CV_SM_T), tap + d0 * (TAPB / 16), CV_CPB * TAPB, cnt + 48);
            mbar_expect_tx(cnt + 48, CV_CPB * TAPB);
        }
        CV_IDX
        const int wgu = (warp >> 2) & 1, g = lane >> 2, ti = lane & 3;
        CST(1);
        if (warp > 8 && elect()) {
            if (warp < 15) mbar_init(cnt + 8 * (warp - 9), warp == 14 ? 8 : 4);
            else if (layer) prefetch_tmap(&tmOut);
        }
        if (warp < 13 && lane < 17 - (warp == 12)) {
            const int off = warp == 12 ? CV_SM_U : CV_SM_B + (warp == 11 ? BX_7 : (warp - 8) * BX_3), str = warp == 12 ? ULEN * 2 : BX_LEN;
#pragma unroll
            for (int c = 0; c < CV_CPB; c++) *reinterpret_cast<uint4*>(sm + off + c * str + 16 * lane) = make_uint4(0, 0, 0, 0);
        }
        fence_async_smem();
        asm volatile("bar.arrive 3, 512;" ::: "memory");
        asm volatile("bar.sync 1, 256;" ::: "memory");
        TSTAMP1X(10, 256);
        asm volatile("setmaxnreg.inc.sync.aligned.u32 168;");
        const uint32_t Tc = smem_u32(sm + CV_SM_T) + (16 + 128 * (warp & 2) + 8 * (warp & 1) + g - 2 * ti) * 4;
        uint2 fa[8][2], fn[8][2];
        auto near_taps = [&](uint2 (&f)[8][2], int c) {
#pragma unroll
            for (int m = 0; m < 16; m++) f[m >> 1][m & 1] = make_uint2(lds1v(Tc + c * TAPB + 64 * (m >> 1) - 32 * (m & 1)), lds1v(Tc + c * TAPB + 64 * (m >> 1) - 32 * (m & 1) + 512));
        };
        CST(6);
        mbar_wait(cnt + 48, 0);
        TSTAMP1X(11, 256); CST(5);
        near_taps(fa, 3 * wgu);
        near_taps(fn, 2 - wgu);
        const int hc = wgu ? warp & 3 : 4;
        const Lc lc = lane_consts(lane, hc);
        TSTAMP1X(12, 256); CST(0);
        uint32_t ya = smem_u32(sm + CV_SM_Y) + wgu * 8192 + (warp & 2) * 2048 + usw(2 * lane + (warp & 1)) * 16;
        uint64_t db = make_desc(smem_u32(Us + wgu * ULEN + UPADF), 16, 256, 3);
        if (wgu) asm volatile("bar.sync 6, 384;" ::: "memory");
        int c = wgu;
        auto chain = [&](const uint2 (&f)[8][2], auto&& meanwhile) {
            float acc[64];
            asm volatile("bar.sync %0, %1;" ::"r"(c ? 4 + wgu : 2), "r"(c ? 256 : 384) : "memory");
            TSTAMPC(1 + 3 * c);
            if (c < 2) CST(7);
            if (c == 0) fence_async_smem();
            wgmma_fence();
#pragma unroll
            for (int m = 0; m < 8; m++) {
                wgmma_rs128(acc, f[m][0], f[m][1], db - (uint64_t)(2 * m), m);
                if (m == CV_HAND && c < 4) asm volatile("bar.arrive %0, 256;" ::"r"(5 - wgu) : "memory");
            }
            wgmma_commit();
            asm volatile("griddepcontrol.launch_dependents;" ::: "memory");
            TSTAMPC(2 + 3 * c); CST(13 + (c >> 1));
            meanwhile();
            wgmma_wait<0>();
            TSTAMPC(3 + 3 * c); CST(10 + (c >> 1));
            uint32_t w[16];
#pragma unroll
            for (int j = 0; j < 16; j++) w[j] = j ? pack2(acc[4 * j] + acc[4 * j - 2], acc[4 * j + 1] + acc[4 * j - 1]) : pack2(acc[0], acc[1]);
#pragma unroll
            for (int j = 0; j < 16; j += 4) stsm_x4_t(ya + 256 * j, w[j], w[j + 1], w[j + 2], w[j + 3]);
            __syncwarp();
            if (lane == 0) mbar_arrive(cnt + 8 * c);
            c += 2; ya += 16384; db += ULEN / 4;
        };
        const uint32_t e4 = lc.e4, e8 = e4 + 428 - 4 * g;
        uint2 fl[4];
        uint32_t kk;
#pragma unroll 1
        for (;;) {
            if (c != 1) chain(fa, [&] {
                if (c == 3 || warp + c == 12) {
#pragma unroll
                    for (int k = 0; k < 19; k++) (k < 16 ? fn[(k >> 1) & 7][k & 1] : fl[k & 3]) = make_uint2(lds1(k < 10 ? e4 + 32 * k + 16 : e8 + 32 * k - 304), lds1(k < 10 ? e4 + 32 * k : e8 + 32 * k - 320));
                    fl[3] = make_uint2(lds1(lc.en), lds1(lc.en - 32));
                    kk = lds1(smem_u32(sm + CV_SM_T) + TAPB * hc + TAPE + 1672);
                }
            });
            if (c > 4) break;
            if (c == 2) { asm volatile("bar.sync 7, 384;" ::: "memory"); fence_async_smem(); }
            chain(fn, [&] { if (c == 2) near_taps(fa, 4); });
        }
        TSTAMP1X(6, 256); CST(2);
        if (wgu || warp == 8) {
            constexpr int seq[29] = {5, 6, 32, 7, 33, 8, 34, 9, 35, 10, 36, 11, 12, 13, 14, 15, 16, 17, 37, 18, 38, 19, 20, 21, 39, 22, 40, 23, 24};
            uint2 f[20];
#pragma unroll
            for (int k = 0; k < 20; k++) f[k] = k < 16 ? fn[(k >> 1) & 7][k & 1] : fl[k & 3];
            far(Int<10>(), seq, lc, hc, lane, f, kk);
        }
    } else {
        asm volatile("setmaxnreg.dec.sync.aligned.u32 88;");
        CV_IDX
        CST(5);
        const uint4* ppv = piv + tid;
        const float4* psv = sum + tid;
        const uint2* pxv = reinterpret_cast<const uint2*>(x1T + (size_t)d0 * XCP) + (tid >> 4) * 32 + (tid & 15);
        asm volatile("st.shared.u64 [%0], %1;" ::"r"(smem_u32(sm + CV_SM_O) + tid * 16), "l"((uint64_t)ppv ^ (uint64_t)psv ^ (uint64_t)pxv) : "memory");
        const int tc = (0x04302100 >> (4 * warp)) & 7;
        const Lc lc = lane_consts(lane, tc);
        pdl_sync();
        SPAN(3 + 4 * layer, 1);
        TSTAMP(0); CST(0);
        if (tid == 0) TSTAMPC(0);
        if (threadIdx.x == 0) { GSTAMP(g_tim, 15); }
        float4 sv[4];
        uint4 pv;
#pragma unroll
        for (int k = 0; k < 4; k++)
            asm volatile(CV_LD ".v4.f32 {%0,%1,%2,%3}, [%4];" : "=f"(sv[k].x), "=f"(sv[k].y), "=f"(sv[k].z), "=f"(sv[k].w) : "l"(psv + 256 * k) : "memory");
        asm volatile(CV_LD ".v4.u32 {%0,%1,%2,%3}, [%4];" : "=r"(pv.x), "=r"(pv.y), "=r"(pv.z), "=r"(pv.w) : "l"(ppv) : "memory");
        uint2 xe[CV_CPB], xo[CV_CPB];
#pragma unroll
        for (int c = 0; c < CV_NL; c++) {
            asm volatile(CV_LD ".v2.u32 {%0,%1}, [%2];" : "=r"(xe[c].x), "=r"(xe[c].y) : "l"(pxv + c * (XCP / 4)) : "memory");
            asm volatile(CV_LD ".v2.u32 {%0,%1}, [%2];" : "=r"(xo[c].x), "=r"(xo[c].y) : "l"(pxv + c * (XCP / 4) + 16) : "memory");
        }
#define CV_XD 300
#define CV_XW 0
        if (warp == CV_XW) {
            if (elect()) {
                const uint32_t c0 = clock();
                mbar_init(cnt + 56, 1);
                asm volatile("fence.mbarrier_init.release.cluster;" ::: "memory");
                mbar_expect_tx(cnt + 56, CV_CPB * 4096);
                while (clock() - c0 < CV_XD) ;
#pragma unroll
                for (int c = CV_NL; c < CV_CPB + CV_NL; c++) bulk_load(smem_u32(Xs + (c % CV_CPB) * XLEN), x1T + (size_t)(d0 + c % CV_CPB) * XCP, 4096, cnt + 56);
            }
            __syncwarp();
            CST(15);
        }
        uint32_t mw[4];
        float rs[8];
#pragma unroll
        for (int k = 0; k < 4; k++) {
            const uint32_t pw = k == 0 ? pv.x : k == 1 ? pv.y : k == 2 ? pv.z : pv.w;
            uint32_t vr;
            mw[k] = pack2(sv[k].x + __uint_as_float(pw << 16), sv[k].z + __uint_as_float(pw & 0xffff0000u));
            asm("cvt.rn.relu.bf16x2.f32 %0, %1, %2;" : "=r"(vr) : "f"(fmaf(-sv[k].z, sv[k].z, sv[k].w)), "f"(fmaf(-sv[k].x, sv[k].x, sv[k].y)));
            const uint32_t ve = pack2(__uint_as_float(vr << 16) + 1e-5f, __uint_as_float(vr & 0xffff0000u) + 1e-5f);
            const uint32_t sd = pack2(sqrt_apx(__uint_as_float(ve << 16)), sqrt_apx(__uint_as_float(ve & 0xffff0000u)));
            rs[2 * k] = rcp_apx(__uint_as_float(sd << 16)); rs[2 * k + 1] = rcp_apx(__uint_as_float(sd & 0xffff0000u));
        }
        if (rs[0] != 123.f) TSTAMP(13);
        const uint32_t ua = smem_u32(Us) + usw(tid + UPADF / 8) * 16;
        uint32_t uw[CV_CPB][4];
#pragma unroll
        for (int c = 0; c < CV_CPB; c++) {
            if (c == CV_NL) {
                if (warp == CV_XW) { mbar_wait(cnt + 56, 0); CST(7); }
                asm volatile("bar.sync 10, 256;" ::: "memory");
            }
            if (c == 1 || c == 2) {
#pragma unroll
                for (int k = c; k < (c == 1 ? 2 : CV_CPB); k++) {
 const uint4 v = ldx(smem_u32(Xs + k * XLEN) + (tid >> 4) * 256 + (tid & 15) * 8); xe[k] = make_uint2(v.x, v.y); xo[k] = make_uint2(v.z, v.w); }
            }
            const uint32_t e0 = sub2(xe[c].x, mw[0]), e1 = sub2(xe[c].y, mw[1]), o0 = sub2(xo[c].x, mw[2]), o1 = sub2(xo[c].y, mw[3]);
            uw[c][0] = pack2(__uint_as_float(e0 << 16) * rs[0], __uint_as_float(o0 << 16) * rs[4]); uw[c][1] = pack2(__uint_as_float(e0 & 0xffff0000u) * rs[1], __uint_as_float(o0 & 0xffff0000u) * rs[5]);
            uw[c][2] = pack2(__uint_as_float(e1 << 16) * rs[2], __uint_as_float(o1 << 16) * rs[6]); uw[c][3] = pack2(__uint_as_float(e1 & 0xffff0000u) * rs[3], __uint_as_float(o1 & 0xffff0000u) * rs[7]);
            asm volatile("st.shared.v4.u32 [%0], {%1,%2,%3,%4};" ::"r"(ua + c * ULEN * 2), "r"(uw[c][0]), "r"(uw[c][1]), "r"(uw[c][2]), "r"(uw[c][3]) : "memory");
            if (c < 2) {
                if (c == 1) fence_async_smem();
                asm volatile("bar.arrive %0, 384;" ::"r"(2 + 4 * c) : "memory");
                if (layer > 29 - c) __trap();
                CST(11 + c);
            }
        }
        asm volatile("bar.arrive 7, 384;" ::: "memory");
        asm volatile("bar.sync 3, 512;" ::: "memory");
        TSTAMP(1); CST(1);
        {
            auto box = [&](auto c0, auto c1, int chunk, int cb, bool full) {
                const uint32_t ea = smem_u32(Us + cb * ULEN) + usw(chunk + UPADF / 8 + (lane ? 1 : -1)) * 16, bx = smem_u32(sm + CV_SM_B + cb * BX_LEN) + chunk * 16;
                uint32_t lo[CV_CPB][4], hi[CV_CPB][2];
#pragma unroll
                for (int c = c0; c < c1; c++) {
                    lo[c][0] = 0;
#pragma unroll
                    for (int k = 1; k < 4; k++) lo[c][k] = __shfl_up_sync(~0u, uw[c][k], 1);
#pragma unroll
                    for (int k = 0; k < 2; k++) hi[c][k] = __shfl_down_sync(~0u, uw[c][k], 1);
                }
#pragma unroll
                for (int c = c0; c < c1; c++)
                    asm volatile("{\n.reg .pred p, q;\nsetp.eq.s32 p, %7, 0;\nsetp.eq.s32 q, %7, 31;\n@p ld.shared.v4.u32 {%0,%1,%2,%3}, [%6];\n@q ld.shared.v2.u32 {%4,%5}, [%6];\n}"
                                 : "+r"(lo[c][0]), "+r"(lo[c][1]), "+r"(lo[c][2]), "+r"(lo[c][3]), "+r"(hi[c][0]), "+r"(hi[c][1]) : "r"(ea + c * ULEN * 2), "r"(lane) : "memory");
#pragma unroll
                for (int c = c0; c < c1; c++) {
                    const uint32_t e[9] = {lo[c][1], lo[c][2], lo[c][3], uw[c][0], uw[c][1], uw[c][2], uw[c][3], hi[c][0], hi[c][1]};
                    uint32_t o[8], p[8], t[7], b3[5], b5[7];
#pragma unroll
                    for (int i = 0; i < 8; i++) { o[i] = __byte_perm(e[i], e[i + 1], 0x5432); p[i] = add2(e[i], o[i]); }
#pragma unroll
                    for (int i = 0; i < 5; i++) b3[i] = add2(o[i], p[i + 1]);
                    sts4(bx + c * BX_LEN + BX_3 + 160, b3);
#pragma unroll
                    for (int i = 1; i < 7; i++) { t[i] = add2(p[i], p[i + 1]); b5[i] = add2(t[i], e[i + 2]); }
                    sts4(bx + c * BX_LEN + BX_5 + 160, b5 + 2);
                    if (full) {
#pragma unroll
                        for (int i = 1; i < 5; i++) { b3[i] = add2(b3[i], t[i + 2]); t[i] = add2(t[i], b5[i + 2]); }
                        sts4(bx + c * BX_LEN + BX_7 + 272, b3 + 1);
                        sts4(bx + c * BX_LEN + BX_9 + 272, t + 1);
                    }
                }
            };
            auto reload = [&](int c, uint32_t a) { const uint4 v = lds4(a); uw[c][0] = v.x; uw[c][1] = v.y; uw[c][2] = v.z; uw[c][3] = v.w; };
            if (warp >= 6) {
#pragma unroll
                for (int c = 0; c < 3; c++) reload(c, ua - 1024 + (c + 2) * ULEN * 2);
            }
            if (warp >= 4) {
#pragma unroll
                for (int c = 3; c < 5; c++) reload(c, ua - 2048 + c * ULEN * 2);
            }
            box(Int<0>(), Int<3>(), warp < 6 ? tid : tid - 64, warp < 6 ? 0 : 2, warp < 4);
            if (warp >= 4) box(Int<3>(), Int<5>(), tid - 128, 0, true);
            else if (tid >= 128 - CV_CPB) {
                const int c = 127 - tid;
                const uint2 v = *reinterpret_cast<const uint2*>(Us + c * ULEN + UPADF);
                const float s1 = __uint_as_float(v.x << 16), s2 = s1 + __uint_as_float(v.x & 0xffff0000u), s3 = s2 + __uint_as_float(v.y << 16), s4 = s3 + __uint_as_float(v.y & 0xffff0000u);
                unsigned char* bc = sm + CV_SM_B + c * BX_LEN;
                *reinterpret_cast<uint32_t*>(bc + BX_5 + 156) = pack2(s1, s2);
                *reinterpret_cast<uint2*>(bc + BX_7 + 264) = make_uint2(v.x << 16, pack2(s2, s3));
                *reinterpret_cast<uint2*>(bc + BX_9 + 264) = make_uint2(pack2(s1, s2), pack2(s3, s4));
            }
        }
        __syncwarp();
        if (lane == 0) mbar_arrive(cnt + 40);
        TSTAMP(2); CST(2);
        if (layer && blockIdx.x == 0 && tid == 224) g_epoch = ld_epoch();
        __syncwarp();
        if ((0x6e >> warp) & 1) {
            constexpr int seq[16] = {0, 1, 2, 3, 4, 5, 6, 32, 7, 8, 9, 33, 10, 34, 11, 12};
            uint2 f[20];
            mbar_wait(cnt, 0);
            const uint32_t e8 = lc.e4 + 428 - (lane & 28);
#pragma unroll
            for (int k = 0; k < 13; k++) f[k] = make_uint2(lds1(k < 10 ? lc.e4 + 32 * k + 16 : e8 + 32 * k - 304), lds1(k < 10 ? lc.e4 + 32 * k : e8 + 32 * k - 320));
            f[19] = make_uint2(lds1(lc.en), lds1(lc.en - 32));
            far(Int<4>(), seq, lc, tc, lane, f, lds1(smem_u32(sm + CV_SM_T) + TAPB * tc + TAPE + 1672));
        }
    }
    {
        CV_IDX
        if ((0xc91 >> warp) & 1) {
            const int c = __popc(0xc91 & ((1 << warp) - 1));
            uint4 xv[2], yv[2];
#pragma unroll
            for (int k = 0; k < 2; k++) xv[k] = ldx(smem_u32(Xs + c * XLEN) + 512 * k + (lane >> 4) * 256 + (lane & 15) * 8);
            const uint32_t u0 = lds1(smem_u32(Us + c * ULEN) + (lane == 31 ? UPADF * 2 : 0));
            mbar_wait(cnt + 8 * c, 0);
#pragma unroll
            for (int k = 0; k < 2; k++) yv[k] = lds4(smem_u32(sm + CV_SM_Y) + c * 8192 + 512 * k + usw(lane) * 16);
            const uint4 yz = lds4(smem_u32(sm + CV_SM_Y) + c * 8192 + 4096 + usw(lane) * 16);
            const float kk = __uint_as_float(lds1(smem_u32(sm + CV_SM_T) + TAPB * c + TAPE + 1272) << 16);
            yv[1].x = add2(yv[1].x, yz.x); yv[1].y = add2(yv[1].y, yz.y); yv[1].z = add2(yv[1].z, yz.z);
            yv[1].w = pack2(fmaf(kk, __uint_as_float(u0 << 16), __uint_as_float(yv[1].w << 16) + __uint_as_float(yz.w << 16)),
                            fmaf(kk, __uint_as_float(u0 << 16) + __uint_as_float(u0 & 0xffff0000u), __uint_as_float(yv[1].w & 0xffff0000u) + __uint_as_float(yz.w & 0xffff0000u)));
#pragma unroll
            for (int k = 0; k < 2; k++) cv_store(dq + c * XCP * 2 + (lane >> 4) * 256 + (lane & 15) * 8 + 512 * k, xv[k], yv[k]);
        }
        TSTAMP(4); CST(8);
        if (layer == 1) {
            const int rb = (blockIdx.x >> 3) + (warp & 8) * 2, cg = blockIdx.x & 7, ch = (tid >> 3) & 31;
            const bf16* src = dst + (size_t)(cg * 80 + ch) * XCP + rb * 64 + (tid & 7) * 8;
            uint32_t v[3][4];
            __syncthreads();
            pause(warp & 8 ? CV_TD1 : CV_TD0);
            uint32_t todo = (warp & 4) ? 3 : 7;
#pragma unroll 1
            for (int it = 0; it < SPIN_MAX; it++) {
#pragma unroll
                for (int k = 0; k < 3; k++)
                    if (todo >> k & 1)
                        asm volatile("ld.relaxed.gpu.global.v4.u32 {%0,%1,%2,%3}, [%4];" : "=r"(v[k][0]), "=r"(v[k][1]), "=r"(v[k][2]), "=r"(v[k][3]) : "l"(src + k * (32 * XCP)) : "memory");
#pragma unroll
                for (int k = 0; k < 3; k++)
                    if ((todo >> k & 1) && v[k][0] != ~0u && v[k][1] != ~0u && v[k][2] != ~0u && v[k][3] != ~0u) {
                        *reinterpret_cast<uint4*>(sm + (32 * k + ch) * 272 + ((tid & 7) + (warp & 8)) * 16) = make_uint4(v[k][0], v[k][1], v[k][2], v[k][3]);
                        todo ^= 1u << k;
                    }
                if (!todo) break;
                __nanosleep(CV_SLEEP);
            }
            __syncwarp();
            asm volatile("bar.sync %0, 256;" ::"r"(8 + (warp >> 3)) : "memory");
            uint32_t w[12];
#pragma unroll
            for (int k = 0; k < 3; k++) ldsm_x4(&w[4 * k], smem_u32(sm) + min(32 * k + lane, 79) * 272 + warp * 16);
            const uint32_t ot = smem_u32(sm + CV_SM_O) + warp * 1280, oa = ot + (lane & 7) * 160 + (lane >> 3) * 16;
            stsm_x4_t(oa, w[0], w[1], w[2], w[3]);
            stsm_x4_t(oa + 64, w[4], w[5], w[6], w[7]);
            asm volatile("stmatrix.sync.aligned.m8n8.x2.trans.shared.b16 [%0], {%1,%2};" ::"r"(oa + 128), "r"(w[8]), "r"(w[9]) : "memory");
            fence_async_smem();
            __syncwarp();
            if (lane == 0) {
                asm volatile("cp.async.bulk.tensor.3d.global.shared::cta.bulk_group [%0, {%1, %2, %3}], [%4];" ::"l"(&tmOut), "r"(cg * 80), "r"((rb >> 1) * 64 + 8 * (warp & 7)), "r"(rb & 1), "r"(ot) : "memory");
                asm volatile("cp.async.bulk.commit_group;" ::: "memory");
                asm volatile("cp.async.bulk.wait_group.read 0;" ::: "memory");
            }
        }
    }
    TSTAMP(3); CST(9); CST_END;
    GSTAMP(g_tim, 14);
    SPAN(3 + 4 * layer, 3);
}

template <int TA, int TB>
__device__ __forceinline__ void wgmma_n240(float (&d)[120], uint64_t da, uint64_t db, int acc) {
    asm volatile("{\n.reg .pred p;\nsetp.ne.b32 p, %124, 0;\nwgmma.mma_async.sync.aligned.m64n240k16.f32.bf16.bf16 {%0,%1,%2,%3,%4,%5,%6,%7,%8,%9,%10,%11,%12,%13,%14,%15,%16,%17,%18,%19,%20,%21,%22,%23,%24,%25,%26,%27,%28,%29,%30,%31,%32,%33,%34,%35,%36,%37,%38,%39,%40,%41,%42,%43,%44,%45,%46,%47,%48,%49,%50,%51,%52,%53,%54,%55,%56,%57,%58,%59,%60,%61,%62,%63,%64,%65,%66,%67,%68,%69,%70,%71,%72,%73,%74,%75,%76,%77,%78,%79,%80,%81,%82,%83,%84,%85,%86,%87,%88,%89,%90,%91,%92,%93,%94,%95,%96,%97,%98,%99,%100,%101,%102,%103,%104,%105,%106,%107,%108,%109,%110,%111,%112,%113,%114,%115,%116,%117,%118,%119}, %120, %121, p, 1, 1, %122, %123;\n}"
                 : "+f"(d[0]), "+f"(d[1]), "+f"(d[2]), "+f"(d[3]), "+f"(d[4]), "+f"(d[5]), "+f"(d[6]), "+f"(d[7]), "+f"(d[8]), "+f"(d[9]), "+f"(d[10]), "+f"(d[11]), "+f"(d[12]), "+f"(d[13]), "+f"(d[14]), "+f"(d[15]), "+f"(d[16]), "+f"(d[17]), "+f"(d[18]), "+f"(d[19]), "+f"(d[20]), "+f"(d[21]), "+f"(d[22]), "+f"(d[23]), "+f"(d[24]), "+f"(d[25]), "+f"(d[26]), "+f"(d[27]), "+f"(d[28]), "+f"(d[29]), "+f"(d[30]), "+f"(d[31]), "+f"(d[32]), "+f"(d[33]), "+f"(d[34]), "+f"(d[35]), "+f"(d[36]), "+f"(d[37]), "+f"(d[38]), "+f"(d[39]), "+f"(d[40]), "+f"(d[41]), "+f"(d[42]), "+f"(d[43]), "+f"(d[44]), "+f"(d[45]), "+f"(d[46]), "+f"(d[47]), "+f"(d[48]), "+f"(d[49]), "+f"(d[50]), "+f"(d[51]), "+f"(d[52]), "+f"(d[53]), "+f"(d[54]), "+f"(d[55]), "+f"(d[56]), "+f"(d[57]), "+f"(d[58]), "+f"(d[59]), "+f"(d[60]), "+f"(d[61]), "+f"(d[62]), "+f"(d[63]), "+f"(d[64]), "+f"(d[65]), "+f"(d[66]), "+f"(d[67]), "+f"(d[68]), "+f"(d[69]), "+f"(d[70]), "+f"(d[71]), "+f"(d[72]), "+f"(d[73]), "+f"(d[74]), "+f"(d[75]), "+f"(d[76]), "+f"(d[77]), "+f"(d[78]), "+f"(d[79]), "+f"(d[80]), "+f"(d[81]), "+f"(d[82]), "+f"(d[83]), "+f"(d[84]), "+f"(d[85]), "+f"(d[86]), "+f"(d[87]), "+f"(d[88]), "+f"(d[89]), "+f"(d[90]), "+f"(d[91]), "+f"(d[92]), "+f"(d[93]), "+f"(d[94]), "+f"(d[95]), "+f"(d[96]), "+f"(d[97]), "+f"(d[98]), "+f"(d[99]), "+f"(d[100]), "+f"(d[101]), "+f"(d[102]), "+f"(d[103]), "+f"(d[104]), "+f"(d[105]), "+f"(d[106]), "+f"(d[107]), "+f"(d[108]), "+f"(d[109]), "+f"(d[110]), "+f"(d[111]), "+f"(d[112]), "+f"(d[113]), "+f"(d[114]), "+f"(d[115]), "+f"(d[116]), "+f"(d[117]), "+f"(d[118]), "+f"(d[119])
                 : "l"(da), "l"(db), "n"(TA), "n"(TB), "r"(acc));
}

__device__ __forceinline__ void wgmma_n80(float (&d)[40], uint64_t da, uint64_t db, int acc) {
    asm volatile("{\n.reg .pred p;\nsetp.ne.b32 p, %42, 0;\nwgmma.mma_async.sync.aligned.m64n80k16.f32.bf16.bf16 {%0,%1,%2,%3,%4,%5,%6,%7,%8,%9,%10,%11,%12,%13,%14,%15,%16,%17,%18,%19,%20,%21,%22,%23,%24,%25,%26,%27,%28,%29,%30,%31,%32,%33,%34,%35,%36,%37,%38,%39}, %40, %41, p, 1, 1, 0, 1;\n}"
                 : "+f"(d[0]), "+f"(d[1]), "+f"(d[2]), "+f"(d[3]), "+f"(d[4]), "+f"(d[5]), "+f"(d[6]), "+f"(d[7]), "+f"(d[8]), "+f"(d[9]), "+f"(d[10]), "+f"(d[11]), "+f"(d[12]), "+f"(d[13]), "+f"(d[14]), "+f"(d[15]), "+f"(d[16]), "+f"(d[17]), "+f"(d[18]), "+f"(d[19]), "+f"(d[20]), "+f"(d[21]), "+f"(d[22]), "+f"(d[23]), "+f"(d[24]), "+f"(d[25]), "+f"(d[26]), "+f"(d[27]), "+f"(d[28]), "+f"(d[29]), "+f"(d[30]), "+f"(d[31]), "+f"(d[32]), "+f"(d[33]), "+f"(d[34]), "+f"(d[35]), "+f"(d[36]), "+f"(d[37]), "+f"(d[38]), "+f"(d[39])
                 : "l"(da), "l"(db), "r"(acc));
}

constexpr int A1_THREADS = 384;
constexpr int A1_NST = 4;
#define A1_SKEW 8
constexpr int A1_STAGE = 16384 + WQ_STAGE;
constexpr int A1_KVP = 336;
constexpr int A1_SM_KV = 2 * A1_STAGE;
constexpr int A1_SM_END = A1_NST * A1_STAGE;
constexpr int A1_SM_BAR = A1_SM_END + 3072 + 3 * WOB + 64;
constexpr int A1_SM_RS = A1_SM_END + 512;
constexpr int A1_SM_W0 = A1_SM_END + 3072, A1_SM_W3 = A1_SM_END - 3 * WOB, A1_SM_A1 = 2 * WOB, A1_SM_A0 = A1_SM_A1 + 61440;
constexpr int A1_SM_XA = A1_SM_W0 + 2 * WOB, A1_SM_XB = A1_SM_XA + 2048;
constexpr int A1_SMEM = A1_SM_BAR + 512 + 7 * CST_EXTRA / 4;
static_assert(A1_SM_W3 >= A1_SM_KV + 144 * A1_KVP && A1_SM_W3 % 512 == 0 && A1_SM_A1 % 1024 == 0 && A1_SM_A0 <= A1_SM_KV && A1_SM_A0 + 61440 <= A1_SM_W3 && A1_SMEM <= 232448 && 11 * 4096 <= A1_STAGE, "layout");
__device__ __forceinline__ constexpr uint32_t wo_off(int h) { return h * WOB + (h < 3 ? A1_SM_W0 : h < 6 ? A1_SM_W3 - 3 * WOB : -6 * WOB); }
#define A1_FRED "red.relaxed.gpu.global.add.u32"
#define A1_FLD "ld.relaxed.gpu.global.u32"
#define ST_SLEEP 20
#define ST_SLEEP0 300
#define A1_P0 2
#define A1_PW (kb - 2)
#define A1_FSPIN SPIN_MAX
#define A1_FSLEEP 40
#define YT_LAYER 1
#define WOT 11
#define A1_P1 550
#define A1_P2 300
#define A1_WOAT 6

template <int L>
__device__ __forceinline__ void a1_mainloop(float (&acc)[120], uint32_t sbase, uint32_t bars, int wg, int tile) {
    constexpr int layer = L; (void)layer;
    const uint64_t da0 = L ? make_desc(sbase + wg * 8192, 8192, 1024, 1) : make_desc(sbase + wg * 8192, 16, 1024, 1), db0 = make_desc(sbase + 16384, 1024, 256, 3);
#pragma unroll 1
    for (int t = 0;; t++) {
        const int st = t % A1_NST;
        mbar_wait(bars + 8 * st, (t / A1_NST) & 1);
        if (t == A1_SKEW && wg == 0) mbar_wait(bars + 160, 0);
        TSTAMP3(1 + t);
        if (t == 0) CSA(0);
        wgmma_fence();
#pragma unroll
        for (int kk = 0; kk < 4; kk++) wgmma_n240<L, 1>(acc, da0 + (uint32_t)(st * (A1_STAGE / 16) + kk * (L ? 128 : 2)), db0 + (uint32_t)(st * (A1_STAGE / 16) + (kk >> 1) * (WQ_STAGE / 32) + (kk & 1) * 32), kk ? 1 : t);
        wgmma_commit();
        if (t == 9) break;
        if (t == A1_SKEW - 1 && wg == 0) wgmma_wait<0>(); else wgmma_wait<1>();
        if (t > 0 && (threadIdx.x & 127) == 0) {
            if (t != A1_SKEW || wg) mbar_arrive(bars + 8 * (A1_NST + (t - 1) % A1_NST));
            if (t == A1_SKEW - 1 && wg == 0) mbar_arrive(bars + 8 * (A1_NST + t % A1_NST));
        }
    }
}

template <bool MAP>
__global__ void __launch_bounds__(A1_THREADS, 1) a1_kernel(const __grid_constant__ Par in, const __grid_constant__ CUtensorMap tmX, const __grid_constant__ CUtensorMap tmR,
                                                           const __grid_constant__ CUtensorMap tmX1, const __grid_constant__ KgMaps tmW, const __grid_constant__ TileTab tab) {
#define layer in.layer
    const unsigned char* const wo = reinterpret_cast<const unsigned char*>(in.wop);
    float2* const rsum = reinterpret_cast<float2*>(in.sum);
    uint4* const of = in.of;
    extern __shared__ __align__(1024) unsigned char stg[];
    const uint32_t sbase = smem_u32(stg);
    const uint32_t bars = sbase + A1_SM_BAR;
    const uint32_t bar_stat = bars + 64, bar_kv = bars + 72, bar_rd = bars + 168;
    const uint32_t bar_wo = bars + 208, bar_done = bars + 216, bar_pv = bars + 224, bar_kvf = bars + 232, bar_f2 = bars + 248, bar_e2 = bars + 384, que = bars + 448;
    const int tid = threadIdx.x;
    CSK(0);
    const int w = __shfl_sync(~0u, tid >> 5, 0), wg = w >> 2;
    uint32_t smid;
    asm volatile("mov.u32 %0, %smid;" : "=r"(smid));
    const uint4 tv = tab.e[(MAP ? smid : blockIdx.x) + (tid & (smid >> 12))];
    const uint64_t pa = reinterpret_cast<const uint64_t*>(&in)[tid & (smid >> 12)], pb = reinterpret_cast<const uint64_t*>(&in)[6 + (tid & (smid >> 12))];
    const bool one = elect();
    uint32_t tz;
    const unsigned char* wq;
    auto entry = [&] { tz = __shfl_sync(~0u, tv.z, 0); wq = (const unsigned char*)(((uint64_t)__shfl_sync(~0u, tv.y, 0) << 32) | __shfl_sync(~0u, tv.x, 0)); };
    auto issue_w = [&](unsigned it) { bulk_load(sbase + (it % A1_NST) * A1_STAGE + 16384, wq + it * WQ_STAGE, WQ_STAGE, bars + 8 * (it % A1_NST)); };
    auto issue_x = [&](unsigned it, int kb) {
        asm volatile("cp.async.bulk.tensor.5d.shared::cluster.global.mbarrier::complete_tx::bytes [%0], [%1, {%3, %3, %3, %4, %5}], [%2];"
                     ::"r"(sbase + (it % A1_NST) * A1_STAGE), "l"(&tmX), "r"(bars + 8 * (it % A1_NST)), "r"(0), "r"(tz & 15), "r"(kb) : "memory");
    };
    auto first_x = [&] {
        issue_x(0, (tz >> 16) & 7); issue_x(1, ((tz >> 16) & 7) + 1);
    };
    auto expect = [&] {
#pragma unroll
        for (int i = 0; i < A1_NST; i++) mbar_expect_tx(bars + 8 * i, A1_STAGE);
    };
    if (w == 8) {
        if (one) {
            prefetch_tmap(&tmX); prefetch_tmap(&tmW.q);
#pragma unroll
            for (int i = 0; i < A1_NST; i++) mbar_init(bars + 8 * i, 1);
            asm volatile("fence.mbarrier_init.release.cluster;" ::: "memory");
        }
        __syncwarp();
        asm volatile("bar.arrive 0, 384;" ::: "memory");
        if (smid >> 12) __trap();
        entry();
        if ((tz & 0x80000010u) == 16) {
            if (one) {
                issue_w(0);
                asm volatile("griddepcontrol.wait;" ::: "memory");
                issue_x(0, (tz >> 16) & 7);
                expect();
                pause(A1_P1);
                issue_w(1);
                issue_x(1, ((tz >> 16) & 7) + 1);
                asm volatile("griddepcontrol.launch_dependents;" ::: "memory");
            }
#pragma unroll
            for (int kb = 2; kb < A1_NST; kb++) {
                __syncwarp();
                mbar_wait(bars + 8 * (kb - 2), 0);
                if (kb == 2) pause(A1_P2);
                if (one) { issue_x(kb, ((tz >> 16) & 7) + kb); issue_w(kb); }
                CSK(6 + kb);
            }
        }
        __syncwarp();
        if (!(tz & 16) && blockIdx.x < 128) kgen_first(in, tmW, sbase + A1_SM_W0, bars - 24, one);
        __syncwarp();
    }
    if (w > 8) CSK(8);
    const bool gen = w != 8 && in.logA && blockIdx.x < 128;
    KgPar kp;
    const int w11 = w < 8 ? 2 * (w & 3) + (w >> 2) : w - 1;
    if (gen) kgen_load(in, reinterpret_cast<const bf16*>(pa), w11, kp);
    if (w > 8) CSK(9);
    if (w == 8) {
        const int tile = tz >> 24, mb = tz & 15, hg = (tz >> 8) & 7, kb0 = (tz >> 16) & 7;
        const unsigned l1 = (tz >> 4) & 1;
        if (__builtin_expect(!l1, 0)) {
            CSK(1);
            const uint32_t ep = ld_epoch();
            if (one) {
                kgen_side(in, sbase + A1_SM_W0, bars - 24);
                if (tile < 128) { first_x(); expect(); }
                asm volatile("cp.async.bulk.wait_group 0;" ::: "memory");
            }
            __syncwarp();
            asm volatile("bar.arrive 10, 96;" ::: "memory");
            CSK(6);
            if (tile < 128) {
                await_all(96 + 32 * hg, ep * 15);
                if (one) issue_w(0);
                __syncwarp();
                mbar_wait(bars, 0);
                if (one) { issue_w(1); issue_x(2, kb0 + 2); issue_w(2); }
            }
            CSK(7);
            asm volatile("bar.sync 3, 384;" ::: "memory");
            if (tile < 128 && one) {
                fence_async_smem();
                issue_x(3, kb0 + 3); issue_w(3);
                mbar_expect_tx(bars + 240, 20480);
                bulk_load(sbase + A1_SM_W0, in.x + (size_t)(mb * 128 + hg * 16) * DM, 20480, bars + 240);
            }
            __syncwarp();
            CSK(9);
        } else asm volatile("bar.sync 3, 64;" ::: "memory");
        if (tile < 128 && elect()) {
#pragma unroll 1
            for (unsigned kb = A1_NST; kb < 10; kb++) {
                mbar_wait(bars + 8 * (A1_NST + kb % A1_NST), ((kb / A1_NST) - 1) & 1);
                if (l1 && kb < 9) mbar_wait(bar_rd + 8 * (kb - A1_NST), 0);
                mbar_expect_tx(bars + 8 * (kb % A1_NST), A1_STAGE);
                issue_x(kb, kb < 5 ? kb + kb0 : kb - kb0); issue_w(kb);
                if (kb == (l1 ? A1_WOAT : 9)) {
                    if (!l1) { mbar_wait(bar_stat, 0); asm volatile("fence.proxy.async.global;" ::: "memory"); }
                    mbar_expect_tx(bar_wo, 8 * WOB);
                    bulk_load(sbase + A1_SM_W0, wo + hg * 8 * WOB, 2 * WOB, bar_wo);
                }
            }
            mbar_wait(bars + 8 * (A1_NST + 3), 1);
            bulk_load(sbase + A1_SM_W3, wo + (hg * 8 + 3) * WOB, 3 * WOB, bar_wo);
        }
        CSA(4); CSA_END;
        return;
    }
    {
        if (w < 8 && one) {
#pragma unroll 1
            for (uint32_t c = (w & 4 ? w & 2 ? 0x1111112'01111111ull : 0x1111111'01111184ull : w & 2 ? 0x3122222'01111111ull : 0x1111132'02220000ull) >> (32 * (w & 1)), b = bars + 56 * w; c; c >>= 4, b += 8)
                if (c & 15) mbar_init(b, c & 15);
            asm volatile("fence.mbarrier_init.release.cluster;" ::: "memory");
        }
        __syncwarp();
        asm volatile("bar.sync 0, 384;" ::: "memory");
        if (layer) {
            if (w == 9) asm volatile("bar.arrive 3, 64;" ::: "memory");
        } else {
            if (gen) { SPAN(0, 0); SPAN(0, 1); kgen_tables(in, reinterpret_cast<uint4*>(stg + 3 * A1_STAGE), w11, kp); }
            else if (w != 11 && w11 > 1) asm volatile("bar.arrive 9, 352;" ::: "memory");
            __syncwarp();
            if (w11 < 2) {
                asm volatile("bar.sync 10, 96;" ::: "memory");
                kgen_sums(in, sbase + A1_SM_W0, w11);
                __syncwarp();
                asm volatile("bar.arrive 9, 352;" ::: "memory");
                CSK(1);
            }
            if (w == 9) asm volatile("bar.sync 3, 384;" ::: "memory"); else asm volatile("bar.arrive 3, 384;" ::: "memory");
        }
    }
    tz = __shfl_sync(~0u, tv.z + (uint32_t)(pb >> 32), 0);
    const int tile = tz >> 24, mb = tz & 15, hg = (tz >> 8) & 7;
    float2* rst = reinterpret_cast<float2*>(stg + A1_SM_RS) + 8;
    if (wg == 2) {
        if (w == 11 && layer == 0) {
            asm volatile("bar.sync 9, 352;" ::: "memory");
            CSK(5);
            if (one) publish(64);
            __syncwarp();
            CSK(6);
        }
        if (tile >= 128) { sm_idle(layer); return; }
        if (w == 10) {
            if (one) { prefetch_tmap(&tmR); prefetch_tmap(&tmX1); }
            uint32_t ns;
            asm volatile("mov.u32 %0, %nsmid;" : "=r"(ns));
            if (MAP && ns != 132) __trap();
        }
        __syncwarp();
        if (w == 9) {
            if (layer && one) {
                mbar_expect_tx(bar_stat, 3840);
                bulk_load(sbase + A1_SM_XB, g_xb + tile * 240, 3840, bar_stat);
            }
            __syncwarp();
            uint4* pre = of + (mb * 8 + hg) * 1280 + (tid - 288);
#pragma unroll 1
            for (int k = 0; k < 5 + 5 * layer; k++) {
#pragma unroll
                for (int i = 0; i < 8; i++) asm volatile("st.global.v4.u32 [%0], {%1,%1,%1,%1};" ::"l"(pre + 32 * i), "r"(~0u) : "memory");
                pre += k < 5 ? 256 : XCP / 8;
                if (k == 4) {
                    CSA(2);
                    asm volatile("fence.acq_rel.gpu;" ::: "memory");
                    asm volatile("fence.proxy.async.global;" ::: "memory");
                    __syncwarp();
                    if (tid == 288) mbar_arrive(bar_done);
                    CSA(3);
                    pre = reinterpret_cast<uint4*>(g_yT) + tile * (5 * XCP / 8) + (tid - 288);
                }
            }
            if (layer == 0) {
                asm volatile("griddepcontrol.launch_dependents;" ::: "memory");
                await_all(64, ld_epoch() * gridDim.x);
                CSA(5);
                float4 a[2] = {};
#pragma unroll
                for (int k = 0; k < 10; k++)
#pragma unroll
                    for (int h = 0; h < 2; h++) {
                        const int c4 = min(tid - 288 + 32 * h, 59);
                        const float4 v = __ldcg(reinterpret_cast<const float4*>(g_csp + (k / 5) * 9600 + (k % 5) * 640 + hg * 80) + c4 + (c4 / 20) * 780);
                        a[h].x += v.x; a[h].y += v.y; a[h].z += v.z; a[h].w += v.w;
                    }
#pragma unroll
                for (int h = 0; h < 2; h++)
#pragma unroll
                    for (int k = 0; k < 4; k++) {
                        const float c = 0.5f * (k == 0 ? a[h].x : k == 1 ? a[h].y : k == 2 ? a[h].z : a[h].w), c1 = c - rbf(c), c2 = c1 - rbf(c1);
                        *reinterpret_cast<uint4*>(stg + A1_SM_XB + (4 * min(tid - 288 + 32 * h, 59) + k) * 16) = make_uint4(pack2(c, c1), pack2(c2, 0.f), 0u, 0u);
                    }
                fence_async_smem();
                __syncwarp();
                if (one) {
                    bulk_store(g_xb + tile * 240, sbase + A1_SM_XB, 3840);
                    asm volatile("cp.async.bulk.commit_group;" ::: "memory");
                    asm volatile("cp.async.bulk.wait_group.read 0;" ::: "memory");
                    mbar_arrive(bar_stat);
                }
                __syncwarp();
                CSA(1);
            }
            TSTAMP1T(9, 288);
        } else {
            const int j = tid - 320;
            const uint32_t tag = ld_epoch();
            if (tid == 352) sm_started(layer);
            const int ch = j & 7, kg = (j >> 3) & 3;
            const unsigned char* src = stg + (layer ? (j >> 5) * 8192 + (hg & 3) * 2048 : A1_SM_W0 + (j >> 2) * 1280);
            const int of0 = layer ? kg * 128 + ((ch ^ kg) << 4) : (j & 7) << 4, ofx = layer ? 576 : 64, ofy = layer ? 1024 : 128;
            float s[8], q[8], p0[8];
#pragma unroll
            for (int i = 0; i < 8; i++) { s[i] = 0.f; q[i] = 0.f; }
#pragma unroll 1
            for (int it = 0; it < 5; it++) {
                uint4 v[4];
                mbar_wait(layer ? bars + 8 * (it % A1_NST) : bars + 240, layer * it / A1_NST);
#pragma unroll
                for (int k = 0; k < 4; k++) v[k] = *reinterpret_cast<const uint4*>(src + (layer ? (it % A1_NST) * A1_STAGE : it * 256) + (k & 1 ? of0 ^ ofx : of0) + (k >> 1) * ofy);
                if (it == 0) {
                    const uint4 pv = *reinterpret_cast<const uint4*>(src + (layer ? ch << 4 : 0));
                    const uint32_t w[4] = {pv.x, pv.y, pv.z, pv.w};
#pragma unroll
                    for (int i = 0; i < 4; i++) { p0[2 * i] = __uint_as_float((layer ? w[i] : w[0]) << 16); p0[2 * i + 1] = __uint_as_float(layer ? w[i] & 0xffff0000u : w[0] << 16); }
                }
                asm volatile("" :: "r"(v[0].x), "r"(v[1].x), "r"(v[2].x), "r"(v[3].x), "f"(p0[0]) : "memory");
                __syncwarp();
                if ((tid & 31) == 0) mbar_arrive(bar_rd + 8 * it);
#pragma unroll
                for (int k = 0; k < 4; k++) {
                    const uint32_t w[4] = {v[k].x, v[k].y, v[k].z, v[k].w};
#pragma unroll
                    for (int i = 0; i < 4; i++) {
                        const float a = __uint_as_float(w[i] << 16) - p0[2 * i], b = __uint_as_float(w[i] & 0xffff0000u) - p0[2 * i + 1];
                        s[2 * i] += a; s[2 * i + 1] += b; q[2 * i] = fmaf(a, a, q[2 * i]); q[2 * i + 1] = fmaf(b, b, q[2 * i + 1]);
                    }
                }
            }
            float o[4];
            int row;
            if (layer == 0) {
                float s0 = ((s[0] + s[1]) + (s[2] + s[3])) + ((s[4] + s[5]) + (s[6] + s[7])), q0 = ((q[0] + q[1]) + (q[2] + q[3])) + ((q[4] + q[5]) + (q[6] + q[7]));
#pragma unroll
                for (int o = 1; o <= 2; o <<= 1) { s0 += __shfl_xor_sync(~0u, s0, o); q0 += __shfl_xor_sync(~0u, q0, o); }
                if ((j & 3) == 0) {
                    const float d = s0 * (1.0f / DM);
                    const uint32_t ms = pack2(p0[0] + d, sqrt_apx(rbf(rbf(fmaxf(fmaf(-d, d, q0 * (1.0f / DM)), 0.f)) + 1e-5f)));
                    asm volatile("st.global.cg.u64 [%0], %1;" ::"l"(g_rstat + mb * 128 + (j & 4) * 16 + hg * 8 + (j >> 3)), "l"(tagw(ms, tag)) : "memory");
                    g_piv[mb * 128 + hg * 16 + ((j >> 2) & 8) + (j & 4) + ((j >> 3) & 3)] = __ushort_as_bfloat16((unsigned short)ms);
                }
                ulonglong2 v;
#pragma unroll 1
                for (int it = 0; it < SPIN_MAX; it++) {
                    v = ld_tag2(reinterpret_cast<const ulonglong2*>(g_rstat + mb * 128) + j);
                    if (__all_sync(~0u, tag_ok(v, tag))) break;
                    __nanosleep(100);
                }
                o[0] = __uint_as_float((uint32_t)v.x << 16); o[1] = rcp_apx(__uint_as_float((uint32_t)v.x & 0xffff0000u));
                o[2] = __uint_as_float((uint32_t)v.y << 16); o[3] = rcp_apx(__uint_as_float((uint32_t)v.y & 0xffff0000u));
                row = 2 * j;
            } else {
#pragma unroll
                for (int i = 0; i < 4; i++) {
                    const bool up = kg & 2;
                    const float ss = __shfl_xor_sync(~0u, up ? s[i] : s[i + 4], 16), qq = __shfl_xor_sync(~0u, up ? q[i] : q[i + 4], 16);
                    s[i] = (up ? s[i + 4] : s[i]) + ss; q[i] = (up ? q[i + 4] : q[i]) + qq; p0[i] = up ? p0[i + 4] : p0[i];
                }
#pragma unroll
                for (int i = 0; i < 2; i++) {
                    const bool up = kg & 1;
                    const float ss = __shfl_xor_sync(~0u, up ? s[i] : s[i + 2], 8), qq = __shfl_xor_sync(~0u, up ? q[i] : q[i + 2], 8);
                    s[i] = (up ? s[i + 2] : s[i]) + ss; q[i] = (up ? q[i + 2] : q[i]) + qq; p0[i] = up ? p0[i + 2] : p0[i];
                }
                uint4* gp = g_halo + 86016 + mb * 512 + j;
                const float d0 = s[0] * (1.0f / 80.0f), d1 = s[1] * (1.0f / 80.0f);
                asm volatile("st.relaxed.gpu.global.v4.f32 [%0], {%1,%2,%3,%4};" ::"l"(gp + hg * 64), "f"(p0[0] + d0), "f"(fmaxf(fmaf(-d0, s[0], q[0]), 0.f)), "f"(p0[1] + d1), "f"(fmaxf(fmaf(-d1, s[1], q[1]), 0.f)) : "memory");
                __nanosleep(ST_SLEEP0);
                uint32_t pw[8][4], todo = 0xff;
#pragma unroll 1
                for (int it = 0; it < SPIN_MAX; it++) {
#pragma unroll
                    for (int k = 0; k < 8; k++)
                        if (todo >> k & 1) asm volatile("ld.relaxed.gpu.global.v4.u32 {%0,%1,%2,%3}, [%4];" : "=r"(pw[k][0]), "=r"(pw[k][1]), "=r"(pw[k][2]), "=r"(pw[k][3]) : "l"(gp + k * 64) : "memory");
#pragma unroll
                    for (int k = 0; k < 8; k++)
                        if (__all_sync(~0u, pw[k][0] != ~0u && pw[k][1] != ~0u && pw[k][2] != ~0u && pw[k][3] != ~0u)) todo &= ~(1u << k);
                    if (!todo) break;
                    __nanosleep(ST_SLEEP);
                }
#pragma unroll
                for (int r = 0; r < 2; r++) {
                    float mean = 0.f, m2 = 0.f;
#pragma unroll
                    for (int k = 0; k < 8; k++) mean += __uint_as_float(pw[k][2 * r]);
                    mean *= 0.125f;
#pragma unroll
                    for (int k = 0; k < 8; k++) {
                        const float dm = __uint_as_float(pw[k][2 * r]) - mean;
                        m2 += fmaf(80.0f * dm, dm, __uint_as_float(pw[k][2 * r + 1]));
                    }
                    o[2 * r] = rbf(mean);
                    o[2 * r + 1] = rcp_apx(rbf(sqrt_apx(rbf(rbf(m2 * (1.0f / DM)) + 1e-5f))));
                }
                row = (j >> 5) * 64 + (j & 7) * 8 + ((j >> 3) & 3) * 2;
                if (hg == 0) *reinterpret_cast<uint32_t*>(g_piv + SEQ + mb * 128 + 2 * (row & 60) + 4 * (row >> 6) + (row & 3)) = __byte_perm(__float_as_uint(o[0]), __float_as_uint(o[2]), 0x7632);
            }
#pragma unroll
            for (int r = 0; r < 2; r++)
                *reinterpret_cast<uint4*>(stg + A1_SM_XA + (row + r) * 16) = make_uint4(__byte_perm(__float_as_uint(-o[2 * r]), 0, 0x3232), __float_as_uint(-o[2 * r]) >> 16, 0u, 0u);
            *reinterpret_cast<float4*>(rst + row + (row >> 6) * 8) = make_float4(o[0], o[1], o[2], o[3]);
            fence_async_smem();
            TSTAMP1T(7, 320); CSA(1);
            if (tid == 320) DBGC(44);
            __syncwarp();
            if ((tid & 31) == 0) mbar_arrive(bar_stat);
        }
        CSA(4); CSA_END;
        if (tid == 320) DBGCAL(0);
        __syncwarp();
        if (w == WOT) {
            mbar_wait(bars + 416, 0);
            mbar_wait(bar_done, 0);
            if (one) {
                bulk_load(sbase, wo + (hg * 8 + 6) * WOB, 2 * WOB, bar_wo);
                bulk_load(sbase + A1_SM_W0 + 2 * WOB, wo + (hg * 8 + 2) * WOB, WOB, bar_wo);
            }
            __syncwarp();
        }
#define FWA 11
#define FWB 10
        if (w == FWA || w == FWB) {
            const int cw = w == FWB;
            const uint32_t* fl = reinterpret_cast<const uint32_t*>(rsum + 2 * SEQ) + (((layer * 16 + mb) * 2 + cw) * 8 + (tid & 7)) * FSTR;
            const unsigned char* src = reinterpret_cast<const unsigned char*>(of) + mb * 163840 + cw * 10240 + (tid & 7) * 20480;
            const uint32_t sl = sbase + (cw ? A1_SM_A1 : A1_SM_A0);
            mbar_wait(cw ? bar_done : bar_kvf, 0);
            if (one) {
                mbar_expect_tx(bar_f2 + 64 * cw + 64, 10240);
                tma_load_3d(sl + 51200, &tmR, layer ? 0 : hg * 80, layer ? hg * 80 : mb * 64, layer ? mb * 2 + cw : cw, bar_f2 + 64 * cw + 64);
            }
            __syncwarp();
            uint32_t pend = 0xffu & ~(1u << hg), v = 0;
            const uint32_t bo = wo_off((tid & 7) + ((tid & 7) < hg)) >> 4, lt = (1u << (tid & 31)) - 1;
#pragma unroll 1
            for (int it = 0; pend && it < 2 * SPIN_MAX; it++) {
                if (v != 4 && (pend >> (tid & 31) & 1)) asm volatile(A1_FLD " %0, [%1];" : "=r"(v) : "l"(fl) : "memory");
                uint32_t fr;
                asm volatile("{\n.reg .pred p;\nmbarrier.test_wait.parity.shared::cta.b64 p, [%1], 0;\nselp.b32 %0, 1, 0, p;\n}" : "=r"(fr) : "r"(bar_e2 + 16 * cw + (tid & 1) * 8) : "memory");
                fr = __ballot_sync(~0u, fr);
                uint32_t m = __ballot_sync(~0u, v == 4 || it >= A1_FSPIN) & pend;
                const int q = 8 - __popc(pend) + __popc(m & lt);
                m &= __ballot_sync(~0u, q < ((fr & 2) ? 8 : (fr & 1) ? 7 : 5));
                pend ^= m;
                if (m >> (tid & 31) & 1) DBGC(12 + cw * 8 + (tid & 7));
                if (!m) __nanosleep(A1_FSLEEP);
                if (m >> (tid & 31) & 1) {
                    bulk_load(q == 7 && !cw ? sbase + A1_SM_W0 : sl + (q < 6 ? q : q - 6) * 10240, src, 10240, bar_f2 + 64 * cw + 8 * q);
                    asm volatile("st.shared.u32 [%0], %1;" ::"r"(que + 32 * cw + 4 * q), "r"(bo) : "memory");
                    mbar_expect_tx(bar_f2 + 64 * cw + 8 * q, 10240);
                    DBGC(44 + cw * 8 + q);
                }
                __syncwarp();
            }
        }
    } else if (tile < 128) {
        SPAN(1 + 4 * layer, 0);
        constexpr int on = 1;
        float acc[120];
        const int lane = tid & 31, warp = w & 7, g = lane >> 2, t = lane & 3;
        if (on) {
            SPAN(1 + 4 * layer, 1);
            TSTAMP1(0);
            if (threadIdx.x == 0) { GSTAMP(g_tim1, 15); }
            TSTAMP3(0);
            if (tid == 0) TSTAMP2(0);
            TSTAMP4(0);
            if (tid == 0) DBGC(60);
            if (layer == 0) a1_mainloop<0>(acc, sbase, bars, wg, tile); else a1_mainloop<1>(acc, sbase, bars, wg, tile);
            uint32_t ok;
            asm volatile("{\n.reg .pred p;\nmbarrier.test_wait.parity.shared::cta.b64 p, [%1], 0;\nselp.b32 %0, 1, 0, p;\n}" : "=r"(ok) : "r"(bar_stat) : "memory");
            if (tid == 128 && !ok) mbar_arrive(bars + 160);
            __syncwarp();
            mbar_wait(bar_stat, 0);
            wgmma_fence();
            wgmma_n240<0, 0>(acc, make_desc(sbase + A1_SM_XA + wg * 1024, 0, 128, 0), make_desc(sbase + A1_SM_XB, 0, 128, 0), 1);
            wgmma_commit();
            if (tid == 128 && ok) mbar_arrive(bars + 160);
            mbar_wait(bars + 8 * (A1_NST + 3), 1);
        }
        uint4* hp = g_halo + (((layer * 16 + mb - ((warp & 3) != 3)) * 8 + hg) * 2 + wg) * 168 + lane;
        float* hr = reinterpret_cast<float*>(hp - lane + 160) + ((warp & 3) == 3 ? g : 2 * t);
        asm volatile("" : "+l"(hp), "+l"(hr));
        const float2* rw = rst + 16 * warp + 8 * wg;
        const float rb0 = rw[g + 8].y, ra = rw[g].y * 0.22360679774997896f, rb = rb0 * 0.22360679774997896f;
        wgmma_wait<0>();
        if ((tid & 127) == 0) mbar_arrive(bar_done);
        TSTAMP1(2); CSA(1);
        TSTAMP1T(13, 224);
        if ((tid & 127) == 0) DBGC(62 - wg);
        uint32_t f[2][30];
#pragma unroll
        for (int j = 10; j < 30; j++) f[1][j] = pack2(acc[4 * j + 2], acc[4 * j + 3]);
        if ((warp & 3) == 3) {
#pragma unroll
            for (int j = 0; j < 20; j += 4) {
                const int a = j < 12 ? 10 + j : 8 + j, b = j == 8 ? 28 : a + 2;
                asm volatile("st.relaxed.gpu.global.v4.u32 [%0], {%1,%2,%3,%4};" ::"l"(hp + 8 * j), "r"(f[1][a]), "r"(f[1][a + 1]), "r"(f[1][b]), "r"(f[1][b + 1]) : "memory");
            }
            if (t == 0) asm volatile("st.relaxed.gpu.global.f32 [%0], %1;" ::"l"(hr), "f"(rb0) : "memory");
        }
        TSTAMP1T(12, 224);
        const uint32_t kvw = sbase + A1_SM_KV + (16 * warp + 8 * wg) * A1_KVP;
        const uint32_t mrow = kvw + (lane & 7) * A1_KVP + (lane >> 3) * 16;
#pragma unroll
        for (int j = 0; j < 20; j += 4) {
            const int a = j < 12 ? 10 + j : 8 + j, b = j == 8 ? 28 : a + 2;
            stsm_x4(mrow + 16 * A1_KVP + 16 * (a - 10) + (j == 8 ? (lane & 16) * 8 : 0), f[1][a], f[1][a + 1], f[1][b], f[1][b + 1]);
        }
        __syncwarp();
        if (lane == 0 && (warp & 3) != 3) mbar_arrive(bar_kv + 8 * (warp + 1));
#pragma unroll
        for (int j = 0; j < 30; j++) f[0][j] = pack2(acc[4 * j], acc[4 * j + 1]);
        stsm_x4(mrow + 8 * A1_KVP + 160, f[0][20], f[0][21], f[0][22], f[0][23]);
        stsm_x4(mrow + 8 * A1_KVP + 224, f[0][24], f[0][25], f[0][26], f[0][27]);
        asm volatile("stmatrix.sync.aligned.m8n8.x2.shared.b16 [%0], {%1,%2};" ::"r"(mrow + 8 * A1_KVP + 288), "r"(f[0][28]), "r"(f[0][29]) : "memory");
#pragma unroll
        for (int j = 0; j < 10; j++) f[1][j] = pack2(acc[4 * j + 2], acc[4 * j + 3]);
        __syncwarp();
        uint32_t vb[10][2], hv[24] = {}, *kp = hv, *vp = hv + 12;
#pragma unroll
        for (int j = 0; j < 10; j += 2) ldsm_x4_t(&vb[j][0], kvw + (8 + (lane & 15)) * A1_KVP + 160 + (lane >> 4) * 16 + 16 * j);
        const bool up0 = 2 * t > g, up1 = 2 * t + 1 > g, edge = (mb | (warp & 3)) == 0;
        float rk[4];
        auto above = [&]() {
            mbar_wait(bar_kv + 8 * warp, 0);
#pragma unroll
            for (int j = 0; j < 12; j += 4) ldsm_x4(&kp[j], mrow + 16 * j);
            rk[0] = rw[2 * t - (up0 ? 8 : 0)].y; rk[1] = rw[2 * t + 1 - (up1 ? 8 : 0)].y;
#pragma unroll
            for (int j = 0; j < 8; j += 4) ldsm_x4_t(&vp[j], mrow + 160 + 16 * j);
            asm volatile("ldmatrix.sync.aligned.m8n8.x2.trans.shared.b16 {%0,%1}, [%2];" : "=r"(vp[8]), "=r"(vp[9]) : "r"(mrow + 288) : "memory");
            __syncwarp();
            if (lane == 0) mbar_arrive(bar_kvf);
        };
        auto ask = [&]() {
            if (mb > 0) {
#pragma unroll
                for (int k = 0; k < 20; k += 4)
                    asm volatile("ld.relaxed.gpu.global.v4.u32 {%0,%1,%2,%3}, [%4];" : "=r"(hv[k]), "=r"(hv[k + 1]), "=r"(hv[k + 2]), "=r"(hv[k + 3]) : "l"(hp + 8 * k) : "memory");
                asm volatile("ld.relaxed.gpu.global.v2.u32 {%0,%1}, [%2];" : "=r"(hv[20]), "=r"(hv[21]) : "l"(hr) : "memory");
            }
        };
        auto halo = [&]() {
            if (lane == 0) mbar_arrive(bar_kvf);
            rk[0] = rw[2 * t].y; rk[1] = rw[2 * t + 1].y;
#pragma unroll 1
            for (int it = 0; it < SPIN_MAX; it++) {
                uint32_t m = max(hv[20], hv[21]);
#pragma unroll
                for (int k = 0; k < 20; k += 2) m = __vimax3_u32(m, hv[k], hv[k + 1]);
                if (!__any_sync(~0u, m == ~0u)) break;
                ask();
            }
            if (wg && lane == 0) mbar_arrive(bars + 416);
            if (up0) rk[0] = __uint_as_float(hv[20]);
            if (up1) rk[1] = __uint_as_float(hv[21]);
#pragma unroll
            for (int j = 0; j < 10; j++) asm volatile("movmatrix.sync.aligned.m8n8.trans.b16 %0, %1;" : "=r"(vp[j]) : "r"(hv[j < 8 ? 12 + j : 2 + j]));
        };
        rk[2] = rw[2 * t + (up0 ? 0 : 8)].y; rk[3] = rw[2 * t + 1 + (up1 ? 0 : 8)].y;
        uint32_t qs[4][2];
#pragma unroll
        for (int h = 0; h < 4; h++) {
            qs[h][0] = (t >> 1) == (h & 1) ? f[0][5 * (h >> 1) + 2] : 0u; qs[h][1] = (t >> 1) == (h & 1) ? f[1][5 * (h >> 1) + 2] : 0u;
            asm volatile("" : "+r"(qs[h][0]), "+r"(qs[h][1]));
        }
#pragma unroll
        for (int j = 0; j < 10; j++) asm volatile("" : "+r"(f[0][j]), "+r"(f[1][j]), "+r"(f[0][10 + j]));
        if (warp & 3) above(); else if (wg) ask(); else hv[20] = mb ? ~0u : 0u;
        TSTAMP1T(10, 64); CSA(2);
        if (warp && !wg) mbar_wait(bars + 416 + 8 * warp, 0);
        CSA(3);
        float sc[4][3][4];
#pragma unroll
        for (int h = 0; h < 4; h++) {
            const int jb = 5 * (h >> 1) + 3 * (h & 1), js = 5 * (h >> 1) + 2;
#pragma unroll
            for (int nt = 1; nt < 3; nt++) {
#pragma unroll
                for (int e = 0; e < 4; e++) sc[h][nt][e] = 0.f;
                mma_bf16(sc[h][nt], f[0][jb], f[1][jb], f[0][jb + 1], f[1][jb + 1], f[nt - 1][10 + jb], f[nt - 1][11 + jb]);
                mma_bf16_k8(sc[h][nt], qs[h][0], qs[h][1], f[nt - 1][10 + js]);
            }
        }
        if (!(warp & 3)) halo();
        TSTAMP1(8); CSA(4);
#pragma unroll
        for (int h = 0; h < 4; h++) {
            const int jb = 5 * (h >> 1) + 3 * (h & 1), js = 5 * (h >> 1) + 2;
#pragma unroll
            for (int e = 0; e < 4; e++) sc[h][0][e] = 0.f;
            mma_bf16(sc[h][0], f[0][jb], f[1][jb], f[0][jb + 1], f[1][jb + 1], kp[jb], kp[jb + 1]);
            mma_bf16_k8(sc[h][0], qs[h][0], qs[h][1], kp[js]);
        }
        TSTAMP1T(3, 64);
        float p[4][4], sum[4][2];
        uint32_t lg[4][2], mx[4];
        const float rl[4] = {rk[0] * ra, rk[1] * ra, rk[2] * rb, rk[3] * rb};
        auto max2 = [](uint32_t a, uint32_t b) { uint32_t r; asm("max.bf16x2 %0, %1, %2;" : "=r"(r) : "r"(a), "r"(b)); return r; };
#pragma unroll
        for (int h = 0; h < 4; h++) {
            lg[h][0] = pack2((up0 ? sc[h][0][0] : sc[h][1][0]) * rl[0], (up0 ? sc[h][1][2] : sc[h][2][2]) * rl[2]);
            lg[h][1] = pack2((up1 ? sc[h][0][1] : sc[h][1][1]) * rl[1], (up1 ? sc[h][1][3] : sc[h][2][3]) * rl[3]);
            if (edge) {
                if (up0) lg[h][0] = __byte_perm(lg[h][0], 0xce6eu, 0x3254);
                if (up1) lg[h][1] = __byte_perm(lg[h][1], 0xce6eu, 0x3254);
            }
            mx[h] = max2(lg[h][0], lg[h][1]);
        }
#pragma unroll
        for (int o = 1; o <= 2; o <<= 1)
#pragma unroll
            for (int h = 0; h < 4; h++) mx[h] = max2(mx[h], __shfl_xor_sync(~0u, mx[h], o));
#pragma unroll
        for (int h = 0; h < 4; h++)
#pragma unroll
            for (int r = 0; r < 2; r++) {
                const float m = __uint_as_float(r ? mx[h] & 0xffff0000u : mx[h] << 16);
#pragma unroll
                for (int e = 0; e < 2; e++)
                    asm("ex2.approx.ftz.f32 %0, %1;" : "=f"(p[h][2 * r + e]) : "f"((__uint_as_float(r ? lg[h][e] & 0xffff0000u : lg[h][e] << 16) - m) * 1.4426950408889634f));
                sum[h][r] = p[h][2 * r] + p[h][2 * r + 1];
            }
#pragma unroll
        for (int o = 1; o <= 2; o <<= 1)
#pragma unroll
            for (int h = 0; h < 4; h++)
#pragma unroll
                for (int r = 0; r < 2; r++) sum[h][r] += __shfl_xor_sync(~0u, sum[h][r], o);
        TSTAMP1T(5, 64); CSA(5);
        const uint32_t mu = (up0 ? 0xffffu : 0u) | (up1 ? 0xffff0000u : 0u);
        uint32_t ob[10][2];
#pragma unroll
        for (int P = 0; P < 2; P++) {
            float os[2][4];
#pragma unroll
            for (int e = 0; e < 2; e++) {
                const int h = 2 * P + e;
                const float i0 = rcp_apx(sum[h][0]), i1 = rcp_apx(sum[h][1]);
                const uint32_t w0 = pack2(p[h][0] * rk[0] * i0, p[h][1] * rk[1] * i0), w1 = pack2(p[h][2] * rk[2] * i1, p[h][3] * rk[3] * i1);
#pragma unroll
                for (int dt = 0; dt < 3; dt++) {
                    const int j = 5 * P + (dt < 2 ? 3 * e + dt : 2);
                    float o[4] = {0.f, 0.f, 0.f, 0.f};
                    mma_bf16(o, w0 & ~mu, w1 & mu, 0u, w1 & ~mu, vb[j][0], vb[j][1]);
                    mma_bf16_k8(o, w0 & mu, 0u, vp[j]);
                    if (dt < 2) { ob[j][0] = pack2(o[0], o[1]); ob[j][1] = pack2(o[2], o[3]); }
                    else { os[e][0] = o[0]; os[e][1] = o[1]; os[e][2] = o[2]; os[e][3] = o[3]; }
                }
            }
#pragma unroll
            for (int k = 0; k < 4; k++) os[0][k] = t < 2 ? os[0][k] : os[1][k];
            ob[5 * P + 2][0] = pack2(os[0][0], os[0][1]); ob[5 * P + 2][1] = pack2(os[0][2], os[0][3]);
        }
        const uint32_t sl = sbase + (wg ? A1_SM_A1 : A1_SM_A0);
        const uint32_t o0 = (warp & 3) * 2048 + g * 64 + ((t ^ (g >> 1)) << 4), o1 = 8192 + (warp & 3) * 512 + g * 32 + ((t ^ ((g >> 2) << 1)) << 3);
        CSA(15);
#pragma unroll
        for (int j = 0; j < 10; j++) asm volatile("" : "+r"(ob[j][0]), "+r"(ob[j][1]) :: "memory");
        if (wg == 0 && lane == 0) mbar_arrive(bar_pv);
        mbar_wait(bar_done, 0);
        if (wg == 0) mbar_wait(bar_kvf, 0);
#pragma unroll
        for (int h = 0; h < 2; h++) {
            asm volatile("st.shared.v4.u32 [%0], {%1,%2,%3,%4};" ::"r"(sl + o0 + h * 1024), "r"(ob[0][h]), "r"(ob[1][h]), "r"(ob[2][h]), "r"(ob[3][h]) : "memory");
            asm volatile("st.shared.v4.u32 [%0], {%1,%2,%3,%4};" ::"r"(sl + o0 + h * 1024 + 512), "r"(ob[4][h]), "r"(ob[5][h]), "r"(ob[6][h]), "r"(ob[7][h]) : "memory");
            asm volatile("st.shared.v2.u32 [%0], {%1,%2};" ::"r"(sl + o1 + h * 256), "r"(ob[8][h]), "r"(ob[9][h]) : "memory");
        }
        if (warp > 4 && lane == 0) mbar_arrive(bars + 384 + 8 * warp);
        fence_async_smem();
        __syncwarp();
        TSTAMP1T(4, 64); CSA(6);
        TSTAMP1(1);
        TSTAMP2(1);
        const unsigned char* ot = reinterpret_cast<const unsigned char*>(of) + mb * 163840 + wg * 10240;
        if (lane == 0) {
            asm volatile("cp.async.bulk.global.shared::cta.bulk_group [%0], [%1], 2048;" ::"l"(ot + hg * 20480 + (warp & 3) * 2048), "r"(sl + (warp & 3) * 2048) : "memory");
            asm volatile("cp.async.bulk.global.shared::cta.bulk_group [%0], [%1], 512;" ::"l"(ot + hg * 20480 + 8192 + (warp & 3) * 512), "r"(sl + 8192 + (warp & 3) * 512) : "memory");
            asm volatile("cp.async.bulk.commit_group;" ::: "memory");
            asm volatile("cp.async.bulk.wait_group 0;" ::: "memory");
            asm volatile(A1_FRED " [%0], 1;" ::"l"(reinterpret_cast<uint32_t*>(rsum + 2 * SEQ) + (((layer * 16 + mb) * 2 + wg) * 8 + hg) * FSTR) : "memory");
            DBGC(4 + warp);
        }
        TSTAMP4(11); CSA(7);
        float ac2[40];
        const uint64_t db0 = make_desc(sbase, 1024, 256, 3), db1 = make_desc(sbase + 10240, 512, 256, 3), da0 = make_desc(sl, 16, 1024, 2), da1 = make_desc(sl + 8192, 16, 256, 3);
        const uint32_t o7 = wg ? 640 : (A1_SM_W0 - A1_SM_A0) >> 4;
        const uint32_t trow = ((lane & 7) + 8 * (lane >> 4)) * 128 + (((2 * (warp & 3) + ((lane >> 3) & 1)) ^ (lane & 7)) << 4);
        uint32_t xr[10][2];
        mbar_wait(bar_f2 + 64 * wg + 64, 0);
        if (layer == 0) {
#pragma unroll
            for (int j = 0; j < 10; j += 2) ldsm_x4(&xr[j][0], sl + 51200 + (16 * (warp & 3) + (lane & 15)) * 160 + (lane >> 4) * 16 + 16 * j);
        } else {
#pragma unroll
            for (int j = 0; j < 10; j += 2) ldsm_x4_t(&xr[j][0], sl + 51200 + trow + 1024 * j);
        }
        const uint32_t ri = __shfl_sync(~0u, layer * SEQ + (wg * 2 + ((g >> 1) & 1)) * 512 + (mb * 16 + 4 * (warp & 3) + (g >> 2)) * 2 + (g & 1), lane);
        mbar_wait(bar_wo, 0);
        if (wg) asm volatile("bar.sync 2, 128;" ::: "memory"); else asm volatile("bar.sync 1, 128;" ::: "memory");
        if (wg) mbar_wait(bar_pv, 0);
        TSTAMP2(2); CSA(8);
#pragma unroll
        for (int q = 0; q < 8; q++) {
            uint32_t bo = wo_off(0) >> 4;
            if (q) {
                mbar_wait(bar_f2 + 64 * wg + 8 * q, 0);
                asm volatile("ld.shared.u32 %0, [%1];" : "=r"(bo) : "r"(que + 32 * wg + 4 * q) : "memory");
                bo = __shfl_sync(~0u, bo, 0);
                TSTAMP4(q);
                if (q % 3 == 1) CSA(9 + q / 3);
                if (q == 1 && (tid & 127) == 0) DBGC(29 + 8 * wg);
            }
            wgmma_fence();
#pragma unroll
            for (int j = 0; j < 5; j++) wgmma_n80(ac2, (j < 4 ? da0 : da1) + (q == 7 ? o7 : 0u) + (uint64_t)((q < 6 ? q * 640 : 0) + (j & 2) * 16 + (j & 1) * 2), (j < 4 ? db0 : db1) + bo + (uint64_t)((j & 2) * 160 + (j & 1) * 32), j || q);
            wgmma_commit();
            if (q == 0) {
                wgmma_wait<0>();
                if ((tid & 127) == 0) { mbar_arrive(bar_e2 + 16 * wg); mbar_arrive(bar_e2 + 8); }
            }
            if (q == 2 && wg) {
                wgmma_wait<1>();
                if (tid == 128) mbar_arrive(bar_e2 + 24);
            }
        }
        if ((tid & 127) == 0) DBGC(28 + wg * 8 + 7);
        TSTAMP2(3);
        wgmma_wait<0>();
        TSTAMP2(4); CSA(12);
        if (__any_sync(~0u, ac2[0] != ac2[0] || ac2[2] != ac2[2])) {
#pragma unroll
            for (int i = 0; i < 40; i++) ac2[i] = 0.f;
            uint32_t a[20], an[20];
            auto lda = [&](uint32_t (&r)[20], int h) {
#pragma unroll
                for (int u = 0; u < 4; u++)
                    asm volatile("ld.relaxed.gpu.global.v4.u32 {%0,%1,%2,%3}, [%4];" : "=r"(r[4 * u]), "=r"(r[4 * u + 1]), "=r"(r[4 * u + 2]), "=r"(r[4 * u + 3]) : "l"(ot + h * 20480 + o0 + u * 512) : "memory");
#pragma unroll
                for (int u = 0; u < 2; u++)
                    asm volatile("ld.relaxed.gpu.global.v2.u32 {%0,%1}, [%2];" : "=r"(r[16 + 2 * u]), "=r"(r[17 + 2 * u]) : "l"(ot + h * 20480 + o1 + u * 256) : "memory");
            };
            lda(an, 0);
#pragma unroll 5
            for (int k = lane; k < WOB / 16; k += 32)
                reinterpret_cast<uint4*>(stg + (sl - sbase))[k] = __ldcg(reinterpret_cast<const uint4*>(wo + hg * 8 * WOB) + k);
            __syncwarp();
#pragma unroll 1
            for (int h = 0; h < 8; h++) {
#pragma unroll 1
                for (int it = 0; it < SPIN_MAX; it++) {
                    uint32_t m = 0;
#pragma unroll
                    for (int k = 0; k < 20; k += 2) m = __vimax3_u32(m, an[k], an[k + 1]);
                    if (!__any_sync(~0u, m == ~0u)) break;
                    lda(an, h);
                }
#pragma unroll
                for (int k = 0; k < 20; k++) a[k] = an[k];
                lda(an, min(h + 1, 7));
                const uint32_t bp = h == hg ? sl : sbase + wo_off(h + (h < hg));
                const int r0 = 8 * ((lane & 7) >> 1) + 2 * (lane >> 3) + (lane & 1), r2 = 4 * ((lane & 7) >> 1) + 2 * ((lane >> 3) & 1) + (lane & 1);
#pragma unroll
                for (int n = 0; n < 10; n++) {
                    uint32_t b[12];
                    ldsm_x4_t(b, bp + (n >> 1) * 1024 + r0 * 32 + (((n ^ (r0 >> 2)) & 1) << 4));
                    ldsm_x4_t(b + 4, bp + 5120 + (n >> 1) * 1024 + r0 * 32 + (((n ^ (r0 >> 2)) & 1) << 4));
                    ldsm_x4_t(b + 8, bp + 10240 + (n >> 1) * 512 + r2 * 32 + (((n ^ (r2 >> 2)) & 1) << 4));
                    mma_bf16(ac2 + 4 * n, a[0], a[8], a[1], a[9], b[0], b[1]); mma_bf16(ac2 + 4 * n, a[2], a[10], a[3], a[11], b[2], b[3]);
                    mma_bf16(ac2 + 4 * n, a[4], a[12], a[5], a[13], b[4], b[5]); mma_bf16(ac2 + 4 * n, a[6], a[14], a[7], a[15], b[6], b[7]);
                    mma_bf16(ac2 + 4 * n, a[16], a[18], a[17], a[19], b[8], b[9]);
                }
            }
        }
#pragma unroll
        for (int j = 0; j < 10; j++)
#pragma unroll
            for (int hh = 0; hh < 2; hh++) {
                const uint32_t a = pack2(ac2[4 * j + 2 * hh], ac2[4 * j + 2 * hh + 1]);
                const __nv_bfloat162 r = __hadd2_rn(*reinterpret_cast<const __nv_bfloat162*>(&xr[j][hh]), *reinterpret_cast<const __nv_bfloat162*>(&a));
                xr[j][hh] = *reinterpret_cast<const uint32_t*>(&r);
            }
        const uint32_t so = sl + 30720;
#pragma unroll
        for (int j = 0; j < 10; j += 2) stsm_x4_t(so + trow + 1024 * j, xr[j][0], xr[j][1], xr[j + 1][0], xr[j + 1][1]);
        if (wg) asm volatile("bar.sync 2, 128;" ::: "memory"); else asm volatile("bar.sync 1, 128;" ::: "memory");
        TSTAMP2(5); CSA(13);
        if ((tid & 127) == 0) {
            fence_async_smem();
            asm volatile("cp.async.bulk.tensor.2d.global.shared::cta.bulk_group [%0, {%1, %2}], [%3];" ::"l"(&tmX1), "r"(mb * 128 + 64 * wg), "r"(hg * 80), "r"(so) : "memory");
            asm volatile("cp.async.bulk.commit_group;" ::: "memory");
        }
        __syncwarp();
        const float p0 = *(volatile const float*)&rw[g].x, p1 = *(volatile const float*)&rw[g + 8].x;
        float s[3][4] = {};
        const uint32_t pp[2] = {__byte_perm(__float_as_uint(p0), 0, 0x3232), __byte_perm(__float_as_uint(p1), 0, 0x3232)};
#pragma unroll
        for (int j = 0; j < 10; j += 2) {
            const uint32_t d0 = sub2(xr[j][0], pp[0]), d1 = sub2(xr[j][1], pp[1]), d2 = sub2(xr[j + 1][0], pp[0]), d3 = sub2(xr[j + 1][1], pp[1]);
            mma_bf16(s[0], xr[j][0], xr[j][1], xr[j + 1][0], xr[j + 1][1], 0x3f803f80u, 0x3f803f80u);
            mma_bf16(s[1], d0, d1, d2, d3, d0, d2);
            mma_bf16(s[2], d0, d1, d2, d3, d1, d3);
        }
        if (t == (g >> 1)) {
            float2* rp = rsum + ri;
            constexpr float idm = 1.0f / DM;
            asm volatile("red.relaxed.gpu.global.add.v2.f32 [%0], {%1, %2};" ::"l"(rp), "f"(fmaf(-80.f, p0, s[0][0]) * idm), "f"(((g & 1) ? s[1][1] : s[1][0]) * idm) : "memory");
            asm volatile("red.relaxed.gpu.global.add.v2.f32 [%0], {%1, %2};" ::"l"(rp + 4), "f"(fmaf(-80.f, p1, s[0][2]) * idm), "f"(((g & 1) ? s[2][3] : s[2][2]) * idm) : "memory");
        }
        asm volatile("cp.async.bulk.wait_group.read 0;" ::: "memory");
        TSTAMP2(6); CSA(14); CSA_END;
        if (tid == 0) DBGC(63);
        if (tid == 128) DBGC(28);
        if (tid == 0) DBGCAL(2);
        GSTAMP(g_tim1, 14);
        SPAN(1 + 4 * layer, 3);
    }
#undef layer
}

static int h_nsm;
static void* h_sym[11];
static TileTab h_tab[2];
static CUtensorMap h_tmX0, h_tmX1, h_tmR0, h_tmR1, h_tmX1st, h_tmOut;
static KgMaps h_tmW;
typedef CUresult (*PFN_encodeTiled)(CUtensorMap*, CUtensorMapDataType, cuuint32_t, void*, const cuuint64_t*, const cuuint64_t*,
                                    const cuuint32_t*, const cuuint32_t*, CUtensorMapInterleave, CUtensorMapSwizzle,
                                    CUtensorMapL2promotion, CUtensorMapFloatOOBfill);
static void make_tmap(CUtensorMap* tm, const void* ptr, uint64_t cols, uint64_t rows, uint32_t bc, uint32_t br, CUtensorMapSwizzle sw, uint64_t pitch = 0, uint64_t hi = 0, uint32_t bh = 2) {
    static PFN_encodeTiled fn = nullptr;
    if (!fn) {
        void* p = nullptr; cudaDriverEntryPointQueryResult qr;
        cudaGetDriverEntryPoint("cuTensorMapEncodeTiled", &p, cudaEnableDefault, &qr);
        fn = (PFN_encodeTiled)p;
    }
    if (br == 0) {
        cuuint64_t dims[5] = {16, 2, rows / 8, 4, cols / 16}; cuuint64_t strides[4] = {cols * 2, cols * 16, cols * 4, 32};
        cuuint32_t box[5] = {16, 2, bc, 4, 5}; cuuint32_t es[5] = {1, 1, 1, 1, 1};
        fn(tm, CU_TENSOR_MAP_DATA_TYPE_BFLOAT16, 5, const_cast<void*>(ptr), dims, strides, box, es, CU_TENSOR_MAP_INTERLEAVE_NONE, sw,
           CU_TENSOR_MAP_L2_PROMOTION_L2_128B, CU_TENSOR_MAP_FLOAT_OOB_FILL_NONE);
        return;
    }
    if (hi == 16) {
        cuuint64_t dims[4] = {16, 32, 120, 20}; cuuint64_t strides[3] = {3840, 32, 32 * 3840};
        cuuint32_t box[4] = {16, 32, 5, 2}; cuuint32_t es[4] = {1, 1, 1, 1};
        fn(tm, CU_TENSOR_MAP_DATA_TYPE_BFLOAT16, 4, const_cast<void*>(ptr), dims, strides, box, es, CU_TENSOR_MAP_INTERLEAVE_NONE, sw,
           CU_TENSOR_MAP_L2_PROMOTION_L2_128B, CU_TENSOR_MAP_FLOAT_OOB_FILL_NONE);
        return;
    }
    if (bh == 0) {
        cuuint64_t dims[5] = {64, 64, 2, 16, 10}; cuuint64_t strides[4] = {pitch * 2, hi * 2, cols * 2, rows * 2};
        cuuint32_t box[5] = {64, 64, 2, 1, 1}; cuuint32_t es[5] = {1, 1, 1, 1, 1};
        fn(tm, CU_TENSOR_MAP_DATA_TYPE_BFLOAT16, 5, const_cast<void*>(ptr), dims, strides, box, es, CU_TENSOR_MAP_INTERLEAVE_NONE, sw,
           CU_TENSOR_MAP_L2_PROMOTION_L2_128B, CU_TENSOR_MAP_FLOAT_OOB_FILL_NONE);
        return;
    }
    if (hi) {
        cuuint64_t dims[3] = {cols, rows, hi == 64 ? 32u : 2u}; cuuint64_t strides[2] = {pitch * 2, hi * 2};
        cuuint32_t box[3] = {bc, br, bh}; cuuint32_t es[3] = {1, 1, 1};
        fn(tm, CU_TENSOR_MAP_DATA_TYPE_BFLOAT16, 3, const_cast<void*>(ptr), dims, strides, box, es, CU_TENSOR_MAP_INTERLEAVE_NONE, sw,
           CU_TENSOR_MAP_L2_PROMOTION_L2_128B, CU_TENSOR_MAP_FLOAT_OOB_FILL_NONE);
        return;
    }
    cuuint64_t dims[2] = {cols, rows}; cuuint64_t strides[1] = {(pitch ? pitch : cols) * 2};
    cuuint32_t box[2] = {bc, br}; cuuint32_t es[2] = {1, 1};
    fn(tm, CU_TENSOR_MAP_DATA_TYPE_BFLOAT16, 2, const_cast<void*>(ptr), dims, strides, box, es, CU_TENSOR_MAP_INTERLEAVE_NONE, sw,
       CU_TENSOR_MAP_L2_PROMOTION_L2_128B, CU_TENSOR_MAP_FLOAT_OOB_FILL_NONE);
}
template <typename... Args>
static void launch_pdl(void (*kern)(Args...), int grid, int block, int smem, Args... args) {
    cudaLaunchConfig_t cfg = {};
    cfg.gridDim = dim3(grid); cfg.blockDim = dim3(block); cfg.dynamicSmemBytes = smem; cfg.stream = cudaStreamPerThread;
    cudaLaunchAttribute at[1];
    at[0].id = cudaLaunchAttributeProgrammaticStreamSerialization; at[0].val.programmaticStreamSerializationAllowed = 1;
    cfg.attrs = at; cfg.numAttrs = 1;
    cudaLaunchKernelEx(&cfg, kern, args...);
}
static void launch_stage(int k, void* const* d_in, void* d_out) {
    const Par par = {k > 1 ? nullptr : (const bf16*)d_in[4], (const bf16*)d_in[5], (const bf16*)d_in[6], (const bf16*)d_in[7], (const bf16*)d_in[8], (const bf16*)d_in[9], k > 1, 0, (const bf16*)d_in[0],
                     (uint4*)h_sym[4], (uint4*)h_sym[2], (uint4*)h_sym[6], (uint4*)h_sym[3], (uint4*)h_sym[0], (float*)h_sym[5], (uint4*)h_sym[1], (const bf16*)d_in[1], (const bf16*)d_in[2]};
    auto a1 = h_nsm == 132 ? a1_kernel<true> : a1_kernel<false>;
    switch (k) {
        case 1: a1<<<h_nsm, A1_THREADS, A1_SMEM, cudaStreamPerThread>>>(par, h_tmX0, h_tmR0, h_tmX1st, h_tmW, h_tab[0]); break;
        case 3: launch_pdl(conv_kernel, DM / CV_CPB, CV_THREADS, CV_SMEM, 0, (const uint4*)h_sym[7], (const float4*)h_sym[4], (const bf16*)h_sym[8], (bf16*)h_sym[9], (const uint4*)h_sym[0], h_tmOut); break;
        case 5: launch_pdl(a1, h_nsm, A1_THREADS, A1_SMEM, par, h_tmX1, h_tmR1, h_tmX1st, h_tmW, h_tab[1]); break;
        case 7: launch_pdl(conv_kernel, DM / CV_CPB, CV_THREADS, CV_SMEM, 1, (const uint4*)h_sym[7] + SEQ / 8, (const float4*)h_sym[4] + SEQ / 2, (const bf16*)h_sym[8], (bf16*)h_sym[10], (const uint4*)h_sym[0], h_tmOut); break;
        default: break;
    }
}
static int n_stage_kernels() { return 9; }
static const char* stage_name(int k) { const char* n[] = {"kgen", "a1", "a2", "conv", "tr", "a1", "a2", "conv", "tr"}; return n[k]; }

extern "C" void kernel_launch(void* const* d_in, const int* in_sizes, int n_in, void* d_out, int out_size) {
    (void)in_sizes; (void)n_in; (void)out_size;
    static const void *p_in = nullptr, *p_w1 = nullptr, *p_w2 = nullptr, *p_out = nullptr;
    if (p_in != d_in[0] || p_w1 != d_in[1] || p_w2 != d_in[2] || p_out != d_out) {
        cudaFuncSetAttribute(conv_kernel, cudaFuncAttributeMaxDynamicSharedMemorySize, CV_SMEM);
        cudaFuncSetAttribute(a1_kernel<true>, cudaFuncAttributeMaxDynamicSharedMemorySize, A1_SMEM);
        cudaFuncSetAttribute(a1_kernel<false>, cudaFuncAttributeMaxDynamicSharedMemorySize, A1_SMEM);
        int dev; cudaGetDevice(&dev); cudaDeviceGetAttribute(&h_nsm, cudaDevAttrMultiProcessorCount, dev);
        if (h_nsm != 132) h_nsm = 128;
        cudaGetSymbolAddress(&h_sym[0], g_tap); cudaGetSymbolAddress(&h_sym[1], g_wq); cudaGetSymbolAddress(&h_sym[2], g_wo);
        cudaGetSymbolAddress(&h_sym[3], g_halo); cudaGetSymbolAddress(&h_sym[4], g_sum); cudaGetSymbolAddress(&h_sym[5], g_csp); cudaGetSymbolAddress(&h_sym[6], g_of);
        cudaGetSymbolAddress(&h_sym[7], g_piv); cudaGetSymbolAddress(&h_sym[8], g_x1T); cudaGetSymbolAddress(&h_sym[9], g_xcT); cudaGetSymbolAddress(&h_sym[10], g_yT);
        for (int i = 0; i < 264; i++) {
            const int s = i % 132, h = (s - 64) >> 1;
            const int t = h_nsm != 132 ? s : s < 64 ? ((s >> 1) & 7) * 16 + (s >> 4) * 2 + (s & 1) : s < 120 ? (1 + h % 7) * 16 + 8 + (h / 7) * 2 + (s & 1) : s < 124 ? 128 : s - 116;
            const int hg = (4 * (t >> 6) + (t & 3)) & 7;
            const uint64_t wp = (uint64_t)h_sym[1] + hg * 10 * WQ_STAGE;
            h_tab[i / 132].e[s] = make_uint4((uint32_t)wp, (uint32_t)(wp >> 32), ((t >> 2) & 15) | (i / 132) << 4 | hg << 8 | 5 * (hg >> 2) << 16 | (uint32_t)t << 24, 0);
        }
        void *px1, *px2;
        cudaGetSymbolAddress(&px1, g_x1T); cudaGetSymbolAddress(&px2, g_xcT);
        make_tmap(&h_tmX0, d_in[0], 128 * 640, 64, 64, 64, CU_TENSOR_MAP_SWIZZLE_128B, 1280, 640, 0);
        make_tmap(&h_tmX1, px2, 128, 64 * XCP, 64, 64, CU_TENSOR_MAP_SWIZZLE_128B, XCP, 64, 0);
        make_tmap(&h_tmR0, d_in[0], 640, 1024, 80, 64, CU_TENSOR_MAP_SWIZZLE_NONE, 1280, 640, 1);
        make_tmap(&h_tmR1, px2, 64, 640, 64, 80, CU_TENSOR_MAP_SWIZZLE_128B, XCP, 64, 1);
        make_tmap(&h_tmX1st, px1, 2048, 640, 64, 80, CU_TENSOR_MAP_SWIZZLE_128B, XCP);
        make_tmap(&h_tmW.q, d_in[1], 16, 640, 16, 32, CU_TENSOR_MAP_SWIZZLE_32B, 1920, 16, 5);
        make_tmap(&h_tmW.o, d_in[2], 640, 640, 4, 0, CU_TENSOR_MAP_SWIZZLE_32B);
        make_tmap(&h_tmW.t, d_in[2], 640, 640, 2, 0, CU_TENSOR_MAP_SWIZZLE_32B);
        make_tmap(&h_tmOut, d_out, 640, 1024, 80, 8, CU_TENSOR_MAP_SWIZZLE_NONE, 1280, 640, 1);
        p_in = d_in[0]; p_w1 = d_in[1]; p_w2 = d_in[2]; p_out = d_out;
    }
    for (int k = 0; k < n_stage_kernels(); k++) launch_stage(k, d_in, d_out);
}
```

```cpp
#include <cuda_runtime.h>
#include <cuda_bf16.h>
#include <cuda_fp16.h>
#include <stdint.h>
#include <cuda.h>

typedef __nv_bfloat16 bf16;

constexpr int SEQ = 2048;
constexpr int DM = 640;
constexpr int NMODE = 192;

__device__ __forceinline__ float bf2f(bf16 v) { return __bfloat162float(v); }
__device__ __forceinline__ float rbf(float v) {
    uint32_t r;
    asm("cvt.rn.bf16x2.f32 %0, %1, %2;" : "=r"(r) : "f"(v), "f"(0.f));
    return __uint_as_float(r);
}
__device__ __forceinline__ uint32_t pack2(float lo, float hi) {
    __nv_bfloat162 t = __floats2bfloat162_rn(lo, hi);
    return *reinterpret_cast<uint32_t*>(&t);
}
__device__ __forceinline__ void pdl_sync() {
    asm volatile("griddepcontrol.wait;" ::: "memory");
    asm volatile("griddepcontrol.launch_dependents;" ::: "memory");
}
__device__ __forceinline__ void pause(uint32_t n) { uint32_t c0, c1; asm volatile("mov.u32 %0, %clock;" : "=r"(c0) :: "memory"); do asm volatile("mov.u32 %0, %clock;" : "=r"(c1) :: "memory"); while (c1 - c0 < n); }
__device__ __forceinline__ float sqrt_apx(float v) { float r; asm("sqrt.approx.ftz.f32 %0, %1;" : "=f"(r) : "f"(v)); return r; }
__device__ __forceinline__ float rcp_apx(float v) { float r; asm("rcp.approx.ftz.f32 %0, %1;" : "=f"(r) : "f"(v)); return r; }
__device__ __forceinline__ uint32_t smem_u32(const void* p) { return (uint32_t)__cvta_generic_to_shared(p); }

constexpr int TAPB = 2944, TAPE = 928;
__device__ __align__(128) uint4 g_tap[DM * TAPB / 16];
#define XPAD 64
constexpr int XCP = SEQ + XPAD;
__device__ __align__(128) bf16 g_x1T[DM * XCP];
__device__ __align__(128) bf16 g_xcT[DM * XCP];
__device__ __align__(128) uint4 g_of[128 * 1280];
constexpr int WQ_STAGE = 240 * 128, WOB = 80 * 160;
__device__ __align__(128) uint4 g_wq[8 * 10 * WQ_STAGE / 16];
__device__ __align__(128) uint4 g_wo[64 * WOB / 16];
__device__ __align__(128) uint4 g_xb[128 * 240];
__device__ __align__(16) float g_csp[10 * 1920];
#define FSTR 32
__device__ __align__(128) float2 g_sum[2 * SEQ + 256 * FSTR];
__device__ __align__(16) bf16 g_piv[2 * SEQ];
__device__ __align__(128) bf16 g_yT[DM * XCP];
__device__ uint32_t g_epoch;
__device__ __align__(16) unsigned long long g_rstat[SEQ];
__device__ __align__(128) uint4 g_halo[640 * 148];
__device__ __forceinline__ unsigned long long tagw(uint32_t payload, uint32_t tag) { return ((unsigned long long)tag << 32) | payload; }
__device__ __forceinline__ ulonglong2 ld_tag2(const ulonglong2* p) {
    ulonglong2 v;
    asm volatile("ld.relaxed.gpu.global.v2.u64 {%0, %1}, [%2];" : "=l"(v.x), "=l"(v.y) : "l"(p) : "memory");
    return v;
}
__device__ __forceinline__ bool tag_ok(ulonglong2 v, uint32_t tag) { return (uint32_t)(v.x >> 32) == tag && (uint32_t)(v.y >> 32) == tag; }
__device__ __forceinline__ uint32_t ld_epoch() { uint32_t v; asm volatile("ld.relaxed.gpu.global.u32 %0, [%1];" : "=r"(v) : "l"(&g_epoch) : "memory"); return v + 1; }
constexpr int SPIN_MAX = 1 << 20;
__device__ __align__(128) uint32_t g_started[11 * 32];
__device__ __forceinline__ void sm_started(int slot) { asm volatile("red.relaxed.gpu.global.add.u32 [%0], 1;" ::"l"(g_started + slot) : "memory"); }
__device__ __forceinline__ void publish(int slot) {
    asm volatile("fence.proxy.async.global;" ::: "memory");
    asm volatile("red.release.gpu.global.add.u32 [%0], 1;" ::"l"(g_started + slot) : "memory");
}
__device__ __forceinline__ void await_all(int slot, uint32_t want) {
#pragma unroll 1
    for (int it = 0; it < SPIN_MAX; it++) {
        uint32_t v;
        asm volatile("ld.acquire.gpu.global.u32 %0, [%1];" : "=r"(v) : "l"(g_started + slot) : "memory");
        if (__all_sync(~0u, (int)(v - want) >= 0)) break;
        __nanosleep(50);
    }
    asm volatile("fence.proxy.async.global;" ::: "memory");
}
__device__ __noinline__ void sm_idle(int slot) {
    if (threadIdx.x != 288) return;
    asm volatile("fence.acq_rel.gpu;" ::: "memory");
    asm volatile("fence.proxy.async.global;" ::: "memory");
    sm_started(slot);
    const uint32_t want = ld_epoch() * gridDim.x;
    pdl_sync();
#pragma unroll 1
    for (int it = 0; it < SPIN_MAX; it++) {
        uint32_t v;
        asm volatile("ld.relaxed.gpu.global.u32 %0, [%1];" : "=r"(v) : "l"(g_started + slot) : "memory");
        if ((int)(v - want) >= 0) break;
        __nanosleep(100);
    }
}
struct TileTab { uint4 e[132]; };
__device__ __forceinline__ bool elect() {
    uint32_t p;
    asm volatile("{\n.reg .pred p;\nelect.sync _|p, 0xffffffff;\nselp.b32 %0, 1, 0, p;\n}" : "=r"(p));
    return p;
}
#define DBG_SYMS
#define TSTAMP(i)
#define TSTAMP1(i)
#define TSTAMP1T(i, t)
#define TSTAMP1X(i, t)
#define SPAN(k, i)
#define GSTAMP(arr, i)
#define TSTAMP2(i)
#define TSTAMP3(i)
#define TSTAMP4(i)
#define TSTAMPK(i, t)
#define TSTAMPC(i)
#define DBGC(i)
#define DBGV(i, v)
#define DBGCAL(i)

#define CSK(i)
#define CSK_END
#define CSA(i)
#define CSA_END
#define CST(i)
#define CST_END
#define CST_EXTRA 0
__device__ __forceinline__ void mma_bf16(float* d, uint32_t a0, uint32_t a1, uint32_t a2, uint32_t a3, uint32_t b0, uint32_t b1) {
    asm volatile("mma.sync.aligned.m16n8k16.row.col.f32.bf16.bf16.f32 {%0,%1,%2,%3}, {%4,%5,%6,%7}, {%8,%9}, {%0,%1,%2,%3};"
                 : "+f"(d[0]), "+f"(d[1]), "+f"(d[2]), "+f"(d[3]) : "r"(a0), "r"(a1), "r"(a2), "r"(a3), "r"(b0), "r"(b1));
}
__device__ __forceinline__ void mma_bf16_k8(float* d, uint32_t a0, uint32_t a1, uint32_t b0) {
    asm volatile("mma.sync.aligned.m16n8k8.row.col.f32.bf16.bf16.f32 {%0,%1,%2,%3}, {%4,%5}, {%6}, {%0,%1,%2,%3};"
                 : "+f"(d[0]), "+f"(d[1]), "+f"(d[2]), "+f"(d[3]) : "r"(a0), "r"(a1), "r"(b0));
}
__device__ __forceinline__ void ldsm_x4(uint32_t* r, uint32_t addr) {
    asm volatile("ldmatrix.sync.aligned.m8n8.x4.shared.b16 {%0,%1,%2,%3}, [%4];"
                 : "=r"(r[0]), "=r"(r[1]), "=r"(r[2]), "=r"(r[3]) : "r"(addr));
}

__device__ __forceinline__ void ldsm_x4_t(uint32_t* r, uint32_t addr) {
    asm volatile("ldmatrix.sync.aligned.m8n8.x4.trans.shared.b16 {%0,%1,%2,%3}, [%4];"
                 : "=r"(r[0]), "=r"(r[1]), "=r"(r[2]), "=r"(r[3]) : "r"(addr));
}
__device__ __forceinline__ void mbar_init(uint32_t bar, int count) { asm volatile("mbarrier.init.shared::cta.b64 [%0], %1;" ::"r"(bar), "r"(count)); }
__device__ __forceinline__ void mbar_arrive(uint32_t bar) { asm volatile("mbarrier.arrive.shared::cta.b64 _, [%0];" ::"r"(bar) : "memory"); }
__device__ __forceinline__ void mbar_wait(uint32_t bar, uint32_t parity) {
    asm volatile("{\n.reg .pred p;\nWAIT_LOOP:\n"
                 "mbarrier.try_wait.parity.shared::cta.b64 p, [%0], %1;\n"
                 "@p bra.uni WAIT_DONE;\nbra.uni WAIT_LOOP;\nWAIT_DONE:\n}" ::"r"(bar), "r"(parity) : "memory");
}

__device__ __forceinline__ void mbar_expect_tx(uint32_t bar, uint32_t bytes) {
    asm volatile("mbarrier.arrive.expect_tx.shared::cta.b64 _, [%0], %1;" ::"r"(bar), "r"(bytes) : "memory");
}
__device__ __forceinline__ void tma_load_2d(uint32_t dst, const void* tmap, int c0, int c1, uint32_t bar) {
    asm volatile("cp.async.bulk.tensor.2d.shared::cluster.global.mbarrier::complete_tx::bytes [%0], [%1, {%3, %4}], [%2];"
                 ::"r"(dst), "l"(tmap), "r"(bar), "r"(c0), "r"(c1) : "memory");
}
__device__ __forceinline__ void tma_load_3d(uint32_t dst, const void* tmap, int c0, int c1, int c2, uint32_t bar) {
    asm volatile("cp.async.bulk.tensor.3d.shared::cluster.global.mbarrier::complete_tx::bytes [%0], [%1, {%3, %4, %5}], [%2];"
                 ::"r"(dst), "l"(tmap), "r"(bar), "r"(c0), "r"(c1), "r"(c2) : "memory");
}
__device__ __forceinline__ void fence_async_smem() { asm volatile("fence.proxy.async.shared::cta;" ::: "memory"); }
__device__ __forceinline__ void bulk_load(uint32_t dst, const void* src, uint32_t bytes, uint32_t bar) {
    asm volatile("cp.async.bulk.shared::cluster.global.mbarrier::complete_tx::bytes [%0], [%1], %2, [%3];"
                 ::"r"(dst), "l"(src), "r"(bytes), "r"(bar) : "memory");
}
__device__ __forceinline__ void stsm_x4(uint32_t addr, uint32_t r0, uint32_t r1, uint32_t r2, uint32_t r3) {
    asm volatile("stmatrix.sync.aligned.m8n8.x4.shared.b16 [%0], {%1,%2,%3,%4};" ::"r"(addr), "r"(r0), "r"(r1), "r"(r2), "r"(r3) : "memory");
}
__device__ __forceinline__ void stsm_x4_t(uint32_t addr, uint32_t r0, uint32_t r1, uint32_t r2, uint32_t r3) {
    asm volatile("stmatrix.sync.aligned.m8n8.x4.trans.shared.b16 [%0], {%1,%2,%3,%4};" ::"r"(addr), "r"(r0), "r"(r1), "r"(r2), "r"(r3) : "memory");
}
__device__ __forceinline__ void prefetch_tmap(const void* tmap) { asm volatile("prefetch.tensormap [%0];" ::"l"(tmap) : "memory"); }

__device__ __forceinline__ float2 cexp_at(float wr2, float wi, float p) {
    float er;
    asm("ex2.approx.ftz.f32 %0, %1;" : "=f"(er) : "f"(wr2 * p));
    float th = wi * p;
    const float k = rintf(th * 0.15915494309189535f);
    th = fmaf(k, -6.2831854820251465f, th);
    th = fmaf(k, 1.7484555314695172e-7f, th);
    return make_float2(er * __cosf(th), er * __sinf(th));
}
__device__ __forceinline__ float2 cmul(float2 a, float2 b) {
    return make_float2(fmaf(a.x, b.x, -a.y * b.y), fmaf(a.x, b.y, a.y * b.x));
}
__device__ __forceinline__ float2 csqr(float2 a) { return make_float2(fmaf(a.x, a.x, -a.y * a.y), (a.x + a.x) * a.y); }
__device__ __forceinline__ uint32_t packh(float2 v) {
    uint32_t r;
    asm("cvt.rn.f16x2.f32 %0, %1, %2;" : "=r"(r) : "f"(v.y), "f"(v.x));
    return r;
}
__device__ __forceinline__ uint2 packr(float2 v) { return make_uint2(packh(v), packh(make_float2(-v.y, v.x))); }
__device__ __forceinline__ uint32_t hcmul(uint32_t a, uint2 b) {
    const __half2 x = *reinterpret_cast<const __half2*>(&a);
    const __half2 r = __hfma2(__high2half2(x), *reinterpret_cast<const __half2*>(&b.y), __hmul2(__low2half2(x), *reinterpret_cast<const __half2*>(&b.x)));
    return *reinterpret_cast<const uint32_t*>(&r);
}

struct Par { const bf16 *logA, *Aim, *Cre, *Cim, *logdt, *dsk; int layer, pad; const bf16* x; uint4 *sum, *wop, *of, *halo, *tap; float* csp; uint4* wq; const bf16 *wqkv, *wo; };
struct KgMaps { CUtensorMap q, o, t; };

__device__ __forceinline__ void bulk_prefetch(const void* p, uint32_t bytes) { asm volatile("cp.async.bulk.prefetch.L2.global [%0], %1;" ::"l"(p), "r"(bytes) : "memory"); }
__device__ __forceinline__ void bulk_store(void* dst, uint32_t src, uint32_t bytes) { asm volatile("cp.async.bulk.global.shared::cta.bulk_group [%0], [%1], %2;" ::"l"(dst), "r"(src), "r"(bytes) : "memory"); }
__device__ __forceinline__ void kgen_first(const Par& in, const KgMaps& tm, const uint32_t b0, const uint32_t wbar, const bool one) {
    const uint32_t blk = blockIdx.x, sec = (blk >= 40) + (blk >= 80), it = (blk >> 3) - 5 * sec, up = (blk >> 2) & 1, hi = blk >> 6;
    auto fetch = [&](int h) {
        if (blk < 120) asm volatile("cp.async.bulk.tensor.4d.shared::cluster.global.mbarrier::complete_tx::bytes [%0], [%1, {%3, %3, %4, %5}], [%2];"
                                    ::"r"(b0 + 10240 * h), "l"(&tm.q), "r"(wbar + 8 * h), "r"(0), "r"(sec * 40 + (blk & 7) * 5), "r"(2 * it + 10 * (up ^ h)) : "memory");
    };
    auto fetch_o = [&](int i) {
        asm volatile("cp.async.bulk.tensor.5d.shared::cluster.global.mbarrier::complete_tx::bytes [%0], [%1, {%3, %3, %4, %3, %5}], [%2];"
                     ::"r"(b0 + 20480 + i * 5120), "l"(&tm.o + i), "r"(wbar + 16), "r"(0), "r"((blk & 7) * 10 + (hi + i) * 4), "r"(((blk >> 3) & 7) * 5) : "memory");
    };
    if (one) {
#pragma unroll
        for (int i = 0; i < 3; i++) mbar_init(wbar + 8 * i, 1);
        asm volatile("fence.mbarrier_init.release.cluster;" ::: "memory");
        fetch(0);
    }
    __syncwarp();
    if (blk >> 20) __trap();
    if (one) {
        bulk_prefetch(in.wqkv + blk * 9600, 19200);
        fetch(1);
        bulk_prefetch(in.wo + blk * 3200, 6400);
        fetch_o(0);
        if (hi) fetch_o(1);
        mbar_expect_tx(wbar, 10240); mbar_expect_tx(wbar + 8, 10240); mbar_expect_tx(wbar + 16, 5120 + hi * 2560);
        bulk_prefetch(in.x + blk * 10240, 20480);
    }
}
__device__ __forceinline__ void kgen_side(const Par& in, const uint32_t b0, const uint32_t wbar) {
    const uint32_t blk = blockIdx.x, sec = (blk >= 40) + (blk >= 80), it = (blk >> 3) - 5 * sec, cg = (blk >> 3) & 7, hb = blk & 7;
    unsigned char* dst = reinterpret_cast<unsigned char*>(in.wq) + (hb * 10 + it) * WQ_STAGE + sec * 5120;
    if (blk < 120) {
        mbar_wait(wbar, 0);
        CSK(2);
        bulk_store(dst, b0, 5120); bulk_store(dst + 15360, b0 + 5120, 5120);
        mbar_wait(wbar + 8, 0);
        CSK(3);
        bulk_store(dst + 5 * WQ_STAGE, b0 + 10240, 5120); bulk_store(dst + 5 * WQ_STAGE + 15360, b0 + 15360, 5120);
        asm volatile("cp.async.bulk.commit_group;" ::: "memory");
        asm volatile("cp.async.bulk.wait_group 0;" ::: "memory");
        CSK(4);
        publish(96 + 32 * hb);
        CSK(5);
    }
    if (blk < 128) {
        mbar_wait(wbar + 16, 0);
        bulk_store(reinterpret_cast<unsigned char*>(in.wop) + (cg * 8 + (hb == cg ? 0 : hb + (hb < cg))) * WOB + (blk >> 6) * 5120, b0 + 20480, blk < 64 ? 5120 : 7680);
        asm volatile("cp.async.bulk.commit_group;" ::: "memory");
    }
}
__device__ __forceinline__ void kgen_sums(const Par& in, const uint32_t b0, const int h) {
    const int lane = threadIdx.x & 31, blk = blockIdx.x;
    if (blk < 120) {
        float cs[5][4] = {};
#pragma unroll
        for (int a = 0; a < 4; a++)
#pragma unroll
            for (int j = 0; j < 5; j++) {
                uint32_t w[4];
                ldsm_x4_t(w, b0 + h * 10240 + j * 1024 + ((lane >> 4) * 8 + (lane & 7)) * 32 + ((((lane >> 3) ^ (lane >> 2)) & 1) << 4) + (a >> 1) * 5120 + (a & 1) * 512);
                mma_bf16(cs[j], w[0], w[1], w[2], w[3], 0x3f803f80u, 0x3f803f80u);
            }
#pragma unroll
        for (int j = 0; j < 5; j++)
            if ((lane & 3) < 2) in.csp[(blk + 120 * h) * 80 + j * 16 + (lane >> 2) + 8 * (lane & 3)] = (lane & 3) ? cs[j][2] : cs[j][0];
    }
}
struct KgPar { uint32_t pw[4], ph[4], pdt, pdsk; };
__device__ __forceinline__ void kgen_load(const Par& in, const bf16* logA, const int w11, KgPar& k) {
    const uint32_t o = blockIdx.x * 480 + min(w11 * 48, w11 * 32 + 128), ow = o + (threadIdx.x & 31), oh = o + ow + (w11 < 8 ? 64 : 0);
    k.pdt = reinterpret_cast<const unsigned short*>(in.logdt)[ow / 96];
    k.pdsk = reinterpret_cast<const unsigned short*>(in.dsk)[ow / 96];
#pragma unroll
    for (int i = 0; i < 4; i++) {
        const bf16* p = i == 0 ? logA : i == 1 ? in.Aim : i == 2 ? in.Cre : in.Cim;
        k.pw[i] = reinterpret_cast<const uint32_t*>(p)[ow]; k.ph[i] = reinterpret_cast<const unsigned short*>(p)[oh];
    }
}
__device__ __forceinline__ void kgen_tables(const Par& in, uint4* tabs, const int w11, const KgPar& kp) {
    const int lane = threadIdx.x & 31, grp = min(w11 >> 1, 4), warp = w11 - 2 * grp;
    const int blk = blockIdx.x, d = blk * 5 + grp, tid = warp * 32 + lane;
    uint4* tab = tabs + grp * (2 * 256);
    const uint32_t *pw = kp.pw, *ph = kp.ph;
#pragma unroll
    for (int i = 0; i < 3; i++)
        if (i < 2 || w11 * 32 + lane < 36) asm volatile("st.global.v4.u32 [%0], {%1,%1,%1,%1};" ::"l"(in.halo + blk * 740 + w11 * 32 + lane + 352 * i), "r"(~0u));
    __syncwarp();
    if (w11 == 10) {
        if (lane < 16) in.sum[blk * 16 + lane] = make_uint4(0, 0, 0, 0);
        else if (lane < 20) reinterpret_cast<uint32_t*>(in.sum + 2048)[(blk * 4 + lane - 16) * FSTR] = 0;
    } else if (w11 > 1) asm volatile("bar.arrive 9, 352;" ::: "memory");
#pragma unroll
    for (int i = 0; i < 6; i++) tabs[w11 * 256 + 32 * i + lane] = make_uint4(0, 0, 0, 0);
    __syncwarp();
    CSK(1);
    const uint32_t tw = smem_u32(tabs) + w11 * 4096;
    const int g = lane >> 2, t = lane & 3;
    const int mt = lane >> 3, r = lane & 7;
    const uint32_t st1 = tw + mt * 1024 + r * 16, st2 = tw + (mt & 1) * 1024 + (mt >> 1) * 128 + ((r ^ (mt >> 1)) << 4), st3 = tw + 2048 + mt * 128 + ((r ^ mt) << 4);
    const uint32_t lda = tw + (mt & 1) * 1024 + r * 128 + (((mt >> 1) ^ r) << 4), ldb = tw + (mt >> 1) * 1024 + r * 128 + (((mt & 1) ^ r) << 4), ldc = tw + 2048 + r * 128 + ((mt ^ r) << 4);
    auto ldsm = [](uint32_t* v, uint32_t a) {
        asm volatile("ldmatrix.sync.aligned.m8n8.x4.shared.b16 {%0,%1,%2,%3}, [%4];" : "=r"(v[0]), "=r"(v[1]), "=r"(v[2]), "=r"(v[3]) : "r"(a) : "memory");
    };
    auto mma = [](float* c, const uint32_t* a, const uint32_t* b) {
        asm("mma.sync.aligned.m16n8k16.row.col.f32.f16.f16.f32 {%0,%1,%2,%3}, {%4,%5,%6,%7}, {%8,%9}, {%0,%1,%2,%3};"
            : "+f"(c[0]), "+f"(c[1]), "+f"(c[2]), "+f"(c[3]) : "r"(a[0]), "r"(a[1]), "r"(a[2]), "r"(a[3]), "r"(b[0]), "r"(b[1]));
    };
    asm volatile("st.shared.u32 [%0], %1;" ::"r"(tw + 3072), "r"(st1 ^ st2 ^ st3 ^ lda ^ ldb ^ ldc) : "memory");
    if (in.pad) __trap();
    const float dt = rbf(expf(__uint_as_float(kp.pdt << 16)));
    const uint32_t cm = __vmaxu2(__vmaxu2(pw[2] & 0x7fff7fffu, pw[3] & 0x7fff7fffu), __byte_perm(ph[2], ph[3], 0x5410) & 0x7fff7fffu);
    const int ex = min(max((int)(__float_as_uint(__uint_as_float(__reduce_max_sync(~0u, max(cm << 16, cm & 0xffff0000u))) * dt) >> 23), 20), 240);
    const float scale = __uint_as_float((uint32_t)(127 + 10 + 127 - ex) << 23), unscale = 2.0f * __uint_as_float((uint32_t)(ex - 10) << 23);
    float k2048 = 0.f;
    float acc[5][4] = {};
    uint32_t af[4][4] = {};
    auto rest = [&] {
        uint32_t b[4][4], c[8];
#pragma unroll
        for (int k = 0; k < 4; k++) {
            ldsm(b[k], ldb ^ (k << 5));
            if (!(k & 1)) ldsm(c + 2 * k, ldc ^ (k << 5));
        }
#pragma unroll
        for (int k = 0; k < 4; k++) { mma(acc[2], af[k], b[k]); mma(acc[3], af[k], b[k] + 2); mma(acc[4], af[k], c + 2 * k); }
    };
#pragma unroll 1
    for (uint32_t sel = 0x1076; sel < (grp < 4 ? 0x6000u : 0x4000u); sel += 0x2200) {
        rest();
        auto par = [&](int i) { return __uint_as_float(__byte_perm(pw[i], ph[i], sel)); };
        const float wr2 = -rbf(expf(par(0))) * dt * 1.4426950408889634f, wi = par(1) * dt;
        const float2 y1 = cexp_at(wr2, -wi, 1.f), w64 = cexp_at(wr2, wi, 64.f), y4 = csqr(csqr(y1)), z8 = csqr(make_float2(y4.x, -y4.y)), y128 = csqr(make_float2(w64.x, -w64.y));
        float2 h0 = make_float2(1.f, 0.f), g0 = make_float2(par(2) * dt * scale, -par(3) * dt * scale);
        const float2 v2 = csqr(y128), v3 = cmul(v2, y128), v4 = csqr(v2), v8 = csqr(v4), c8 = cmul(g0, v8);
        const uint2 z64 = packr(w64), v[8] = {make_uint2(packh(c8), 0u), packr(y128), packr(v2), packr(v3), packr(v4), packr(cmul(v4, y128)), packr(csqr(v3)), packr(cmul(v4, v3))};
        k2048 += fmaf(c8.x, v8.x, -c8.y * v8.y);
        uint32_t ge[4];
#pragma unroll
        for (int e = 0; e < 8; e++) {
            const uint32_t p = packh(h0), q = packh(g0);
            if (!(e & 1)) ge[e >> 1] = q;
            stsm_x4((st1 ^ (e << 4)) + e * 128, p, e ? hcmul(p, z64) : z64.x, q, hcmul(q, v[1]));
            if (e < 7) { h0 = e ? cmul(h0, z8) : z8; g0 = cmul(g0, y1); }
        }
        __syncwarp();
        uint32_t b[4][4];
#pragma unroll
        for (int k = 0; k < 4; k++) { ldsm(af[k], lda ^ (k << 5)); ldsm(b[k], (ldb ^ (k << 5)) + 2048); }
#pragma unroll
        for (int e = 0; e < 8; e += 2) {
            stsm_x4((st2 ^ (e << 4)) + e * 128, hcmul(ge[e & 3], v[2 + (e >> 2)]), hcmul(ge[0], v[4 + (e >> 1)]), hcmul(ge[(e & 3) + 1], v[2 + (e >> 2)]), hcmul(ge[2], v[4 + (e >> 1)]));
            if (!(e & 3)) stsm_x4((st3 ^ (e << 4)) + e * 128, e ? hcmul(v[0].x, v[e]) : v[0].x, hcmul(v[0].x, v[e + 1]), hcmul(v[0].x, v[e + 2]), hcmul(v[0].x, v[e + 3]));
            mma(acc[0], af[e >> 1], b[e >> 1]);
            mma(acc[1], af[e >> 1], b[e >> 1] + 2);
        }
        __syncwarp();
        if (sel == 0x1076) CSK(3);
    }
    rest();
#pragma unroll
    for (int e = 0; e < 5; e++) k2048 += __shfl_xor_sync(~0u, k2048, 1 << e);
    {
        float* Pp = reinterpret_cast<float*>(tab + warp * 256);
        auto sw = [](int i) { return i ^ ((i >> 2) & 24); };
#pragma unroll
        for (int h = 0; h < 2; h++) {
            const int b = g + 8 * h;
            *reinterpret_cast<float2*>(Pp + sw(8 * b + 2 * t)) = make_float2(acc[0][2 * h] * unscale, acc[0][2 * h + 1] * unscale);
            *reinterpret_cast<float2*>(Pp + 128 + sw(8 * b + 2 * t)) = make_float2(acc[1][2 * h] * unscale, acc[1][2 * h + 1] * unscale);
            *reinterpret_cast<float2*>(Pp + 256 + sw(4 * b + 2 * (t & 1) + 64 * (t >> 1))) = make_float2(acc[2][2 * h] * unscale, acc[2][2 * h + 1] * unscale);
            *reinterpret_cast<float2*>(Pp + 384 + sw(2 * b + 32 * t)) = make_float2(acc[3][2 * h] * unscale, acc[3][2 * h + 1] * unscale);
            Pp[512 + sw(b + 32 * t)] = acc[4][2 * h] * unscale;
            Pp[512 + sw(b + 32 * t + 16)] = acc[4][2 * h + 1] * unscale;
        }
        if (lane == 0) Pp[640] = k2048 * unscale;
    }
    CSK(4);
    asm volatile("bar.sync %0, %1;" ::"r"(grp + 4), "r"(grp < 4 ? 64 : 96) : "memory");
    if (warp == 2) return;
    const float* Kp = reinterpret_cast<const float*>(tab);
    auto ksum = [&](int i) -> float { return rbf(Kp[i] + Kp[1024 + i] + (grp < 4 ? 0.f : Kp[2048 + i])); };
    auto ksum2 = [&](int q) -> float2 {
        q ^= (q >> 2) & 12;
        const float2 a = reinterpret_cast<const float2*>(Kp)[q], b = reinterpret_cast<const float2*>(Kp)[512 + q];
        const float2 c = grp < 4 ? make_float2(0.f, 0.f) : reinterpret_cast<const float2*>(Kp)[1024 + q];
        return make_float2(a.x + b.x + c.x, a.y + b.y + c.y);
    };
    {
        uint2* W2 = reinterpret_cast<uint2*>(in.tap + d * (TAPB / 16)) + 8;
        uint2* E4 = W2 + (TAPE - 64) / 8;
        float2 v = ksum2(64 * warp + lane), z = ksum2(64 * warp + 32 + lane), y = ksum2(128 + tid);
        const int q = (96 + tid) ^ (((96 + tid) >> 2) & 6);
        const float4 ua = reinterpret_cast<const float4*>(Kp)[q], uc = reinterpret_cast<const float4*>(Kp)[256 + q], ud = grp < 4 ? make_float4(0.f, 0.f, 0.f, 0.f) : reinterpret_cast<const float4*>(Kp)[512 + q];
        const float4 ub = make_float4(uc.x + ud.x, uc.y + ud.y, uc.z + ud.z, uc.w + ud.w);
        const float s1 = ksum(tid == 31 ? 336 : lane ? 384 : 103), s2 = ksum(tid == 31 ? 512 : tid ? 640 : 231);
        if (tid == 0) v.x += __uint_as_float(kp.pdsk << 16);
        if (tid == 63) y.y -= s1;
        const uint32_t lo = pack2(v.x, v.y), hi = pack2(z.x, z.y), tp = pack2(y.x, y.y);
        uint32_t nl = __shfl_sync(~0u, lo, lane - 1), nh = __shfl_sync(~0u, lane == 31 ? lo : hi, lane - 1), nt = __shfl_sync(~0u, tp, lane + 1);
        if (lane == 0) nl = warp ? __float_as_uint(s1) : 0u;
        if (lane == 31) nt = warp ? 0u : __float_as_uint(s1) >> 16;
        W2[64 * warp + lane] = make_uint2(__byte_perm(lo, nl, 0x7610), __byte_perm(lo, 0, 0x1032));
        W2[64 * warp + lane + 32] = make_uint2(__byte_perm(hi, nh, 0x7610), __byte_perm(hi, 0, 0x1032));
        reinterpret_cast<uint4*>(W2)[64 + tid] = make_uint4(__byte_perm(tp, __float_as_uint(s2), tid ? 0x1010 : 0x7610), __byte_perm(tp, 0, 0x1010), __byte_perm(tp, 0, 0x1032), __byte_perm(nt, tp, 0x7610));
        E4[(tid < 32 ? 159 : 209 - 32) + tid] = make_uint2(pack2(ua.x + ub.x, ua.y + ub.y), pack2(ua.z + ub.z, ua.w + ub.w - (tid == 31 ? s2 : 0.f)));
        if (tid == 63) E4[241] = make_uint2(__float_as_uint(s2) >> 16, 0u);
    }
    CSK(5);
    SPAN(0, 3);
}

#define CV_SLEEP 40
#define CV_TD1 500
#define CV_TD0 0
#define CV_LD "ld.relaxed.gpu.global"
#define CV_NL 1
#define CV_D2 3
#define CV_PDH 12
#define CV_PDF 4
#define CV_HAND 7
constexpr int CV_CPB = 5;
constexpr int CV_THREADS = 512;
constexpr int UPADF = 128;
constexpr int ULEN = UPADF + SEQ;
constexpr int XLEN = XCP;
constexpr int BX_5 = 0, BX_3 = 3264, BX_9 = 6528, BX_7 = 8960, BX_LEN = 11392;
constexpr int CV_SM_U = 0;
constexpr int CV_SM_T = CV_CPB * ULEN * 2;
constexpr int CV_SM_B = CV_SM_T + CV_CPB * TAPB;
constexpr int CV_SM_X = CV_SM_B + CV_CPB * BX_LEN;
constexpr int CV_SM_Y = (CV_SM_X + CV_CPB * XLEN * 2 + 127) & ~127;
constexpr int CV_SM_CNT = CV_SM_Y + CV_CPB * 8192;
constexpr int CV_SM_O = CV_SM_CNT + 128;
constexpr int CV_SMEM = CV_SM_O + 20480 + CST_EXTRA;
static_assert(ULEN % 128 == 0 && CV_SM_B % 128 == 0 && CV_SM_CNT % 128 == 0, "layout");

__device__ __forceinline__ uint32_t sub2(uint32_t x, uint32_t m) {
    const __nv_bfloat162 d = __hsub2(*reinterpret_cast<const __nv_bfloat162*>(&x), *reinterpret_cast<const __nv_bfloat162*>(&m));
    return *reinterpret_cast<const uint32_t*>(&d);
}
__device__ __forceinline__ uint32_t add2(uint32_t x, uint32_t y) {
    const __nv_bfloat162 d = __hadd2_rn(*reinterpret_cast<const __nv_bfloat162*>(&x), *reinterpret_cast<const __nv_bfloat162*>(&y));
    return *reinterpret_cast<const uint32_t*>(&d);
}
__device__ __forceinline__ void wgmma_fence() { asm volatile("wgmma.fence.sync.aligned;" ::: "memory"); }
__device__ __forceinline__ void wgmma_commit() { asm volatile("wgmma.commit_group.sync.aligned;" ::: "memory"); }
template <int N> __device__ __forceinline__ void wgmma_wait() { asm volatile("wgmma.wait_group.sync.aligned %0;" ::"n"(N) : "memory"); }
__device__ __forceinline__ uint64_t make_desc(uint32_t addr, uint32_t lbo, uint32_t sbo, uint32_t mode) {
    return (uint64_t)((addr & 0x3FFFF) >> 4) | ((uint64_t)(lbo >> 4) << 16) | ((uint64_t)(sbo >> 4) << 32) | ((uint64_t)mode << 62);
}
__device__ __forceinline__ void wgmma_rs128(float (&d)[64], uint2 hi, uint2 lo, uint64_t db, int acc) {
    asm volatile("{\n.reg .pred p;\nsetp.ne.b32 p, %69, 0;\nwgmma.mma_async.sync.aligned.m64n128k16.f32.bf16.bf16 {%0,%1,%2,%3,%4,%5,%6,%7,%8,%9,%10,%11,%12,%13,%14,%15,%16,%17,%18,%19,%20,%21,%22,%23,%24,%25,%26,%27,%28,%29,%30,%31,%32,%33,%34,%35,%36,%37,%38,%39,%40,%41,%42,%43,%44,%45,%46,%47,%48,%49,%50,%51,%52,%53,%54,%55,%56,%57,%58,%59,%60,%61,%62,%63}, {%64,%65,%66,%67}, %68, p, 1, 1, 0;\n}"
                 : "+f"(d[0]), "+f"(d[1]), "+f"(d[2]), "+f"(d[3]), "+f"(d[4]), "+f"(d[5]), "+f"(d[6]), "+f"(d[7]), "+f"(d[8]), "+f"(d[9]), "+f"(d[10]), "+f"(d[11]), "+f"(d[12]), "+f"(d[13]), "+f"(d[14]), "+f"(d[15]), "+f"(d[16]), "+f"(d[17]), "+f"(d[18]), "+f"(d[19]), "+f"(d[20]), "+f"(d[21]), "+f"(d[22]), "+f"(d[23]), "+f"(d[24]), "+f"(d[25]), "+f"(d[26]), "+f"(d[27]), "+f"(d[28]), "+f"(d[29]), "+f"(d[30]), "+f"(d[31]), "+f"(d[32]), "+f"(d[33]), "+f"(d[34]), "+f"(d[35]), "+f"(d[36]), "+f"(d[37]), "+f"(d[38]), "+f"(d[39]), "+f"(d[40]), "+f"(d[41]), "+f"(d[42]), "+f"(d[43]), "+f"(d[44]), "+f"(d[45]), "+f"(d[46]), "+f"(d[47]), "+f"(d[48]), "+f"(d[49]), "+f"(d[50]), "+f"(d[51]), "+f"(d[52]), "+f"(d[53]), "+f"(d[54]), "+f"(d[55]), "+f"(d[56]), "+f"(d[57]), "+f"(d[58]), "+f"(d[59]), "+f"(d[60]), "+f"(d[61]), "+f"(d[62]), "+f"(d[63])
                 : "r"(hi.x), "r"(hi.y), "r"(lo.x), "r"(lo.y), "l"(db), "r"(acc));
}
template <int V> struct Int { __device__ constexpr operator int() const { return V; } };
__device__ __forceinline__ void sts4(uint32_t a, const uint32_t* v) { asm volatile("st.shared.v4.u32 [%0], {%1,%2,%3,%4};" ::"r"(a), "r"(v[0]), "r"(v[1]), "r"(v[2]), "r"(v[3]) : "memory"); }
__device__ __forceinline__ uint32_t lds1(uint32_t a) { uint32_t v; asm volatile("ld.shared.u32 %0, [%1];" : "=r"(v) : "r"(a) : "memory"); return v; }
__device__ __forceinline__ uint32_t lds1v(uint32_t a) { uint32_t v; asm volatile("ld.volatile.shared.u32 %0, [%1];" : "=r"(v) : "r"(a) : "memory"); return v; }
__device__ __forceinline__ uint4 lds4(uint32_t a) { uint4 v; asm volatile("ld.shared.v4.u32 {%0,%1,%2,%3}, [%4];" : "=r"(v.x), "=r"(v.y), "=r"(v.z), "=r"(v.w) : "r"(a) : "memory"); return v; }
__device__ __forceinline__ uint4 ldx(uint32_t a) {
    uint4 v;
    asm volatile("ld.shared.v2.u32 {%0,%1}, [%4];\nld.shared.v2.u32 {%2,%3}, [%4+128];" : "=r"(v.x), "=r"(v.y), "=r"(v.z), "=r"(v.w) : "r"(a) : "memory");
    return v;
}
__device__ __forceinline__ void cv_store(unsigned char* p, uint4 x, uint4 y) {
    asm volatile("st.relaxed.gpu.global.v2.u32 [%0], {%1,%2};" ::"l"(p), "r"(add2(x.x, __byte_perm(y.x, y.y, 0x5410))), "r"(add2(x.y, __byte_perm(y.z, y.w, 0x5410))) : "memory");
    asm volatile("st.relaxed.gpu.global.v2.u32 [%0], {%1,%2};" ::"l"(p + 128), "r"(add2(x.z, __byte_perm(y.x, y.y, 0x7632))), "r"(add2(x.w, __byte_perm(y.z, y.w, 0x7632))) : "memory");
}
__device__ __forceinline__ int usw(int ch) { return ch ^ ((ch >> 3) & 1); }
__global__ void __launch_bounds__(CV_THREADS, 1) conv_kernel(int layer, const uint4* __restrict__ piv, const float4* __restrict__ sum, const bf16* __restrict__ x1T,
                                                             bf16* __restrict__ dst, const uint4* __restrict__ tap, const __grid_constant__ CUtensorMap tmOut) {
    extern __shared__ __align__(1024) unsigned char sm[];
    SPAN(3 + 4 * layer, 0);
    bf16* Us = reinterpret_cast<bf16*>(sm + CV_SM_U);
    bf16* Xs = reinterpret_cast<bf16*>(sm + CV_SM_X);
#define CV_IDX int tid; asm volatile("mov.u32 %0, %tid.x;" : "=r"(tid)); const int lane = tid & 31, warp = __shfl_sync(~0u, tid >> 5, 0);
    const int d0 = blockIdx.x * CV_CPB, tile = blockIdx.x; (void)tile;
    const uint32_t cnt = smem_u32(sm + CV_SM_CNT);
    struct Lc { uint32_t a4, a8, uc, ud, y, e4, en, sp, ss; int go; };
    auto lane_consts = [&](int lane, int c) {
        const int mat = lane >> 3, r = lane & 7, g = lane >> 2, ti = lane & 3, e = g - 2 * ti;
        const int j2 = 13 + (r ^ 1) + 8 * (mat >> 1), j3 = j2 + 2, i0 = 8 * (mat & 1);
        const uint32_t sb = smem_u32(sm), oc = sb + usw(16 * (mat >> 1) + 2 * r + (mat & 1)) * 16;
        const Lc l = {sb + CV_SM_B + c * BX_LEN + ((j2 & 1) ? BX_3 + (4 * j2 + i0 + 84) * 2 : BX_5 + (4 * j2 + i0 + 80) * 2),
                      sb + CV_SM_B + c * BX_LEN + ((j3 & 1) ? BX_7 : BX_9) + (8 * j3 + i0 + 136) * 2,
                      oc + CV_SM_U + (c * ULEN + UPADF) * 2, sb + CV_SM_U + (c * ULEN + UPADF) * 2 + usw(16 * mat + 2 * r + 2) * 16, oc + CV_SM_Y + c * 8192,
                      sb + CV_SM_T + c * TAPB + TAPE + (307 + 2 * g - ti) * 4, sb + CV_SM_T + c * TAPB + (528 + e) * 4,
                      e == -5 ? 0x4410u : e == -4 ? 0x1044u : 0x4444u, e == 3 ? 0x4410u : e == 4 ? 0x1044u : 0x4444u,
                      c * XCP * 2 + (lane >> 4) * 256 + (lane & 15) * 8};
        asm volatile("st.shared.u32 [%0], %1;" ::"r"(sb + CV_SM_CNT + 120), "r"(l.y ^ l.a4 ^ l.a8 ^ l.uc ^ l.ud ^ l.e4 ^ l.en ^ l.sp ^ l.ss ^ l.go) : "memory");
        return l;
    };
    unsigned char* const dq = reinterpret_cast<unsigned char*>(dst + (size_t)d0 * XCP);
    auto far = [&](auto T0_, const auto& seq, const Lc& lc, int c, int lane, const uint2 (&f)[20], uint32_t kk) {
        constexpr int T0 = T0_, T1 = T0 + 6, TC = T0 > 7 ? T0 : 7, NS = sizeof(seq) / sizeof(seq[0]), PD = T0 > 7 ? CV_PDH : CV_PDF;
        uint32_t bq[28], yw[4], yz[4], P, S;
        uint4 xv, yv;
        asm("prmt.b32 %0, %1, 0, %2;" : "=r"(P) : "r"(kk), "r"(lc.sp));
        asm("prmt.b32 %0, %1, 0, %2;" : "=r"(S) : "r"(kk), "r"(lc.ss));
#pragma unroll
        for (int k = 0; 2 * k < T1 - TC + 4; k++) ldsm_x4(bq + 4 * k, lc.uc + (TC - 8) * 256 + 512 * k);
#pragma unroll
        for (int k = 0; 4 * k < T1 - TC; k++) ldsm_x4(bq + 20 + 4 * k, lc.ud + (TC - 8) * 256 + 1024 * k);
        CST(3);
        mbar_wait(cnt + 8 * c, 0);
        mbar_wait(cnt + 40, 0);
        CST(4);
        float acc[6][4] = {};
        uint32_t a[PD + 1][4];
#pragma unroll
        for (int i = -PD; i < NS + 3; i++) {
            if (i + PD < NS) ldsm_x4_t(a[(i + PD) % (PD + 1)], seq[i + PD] < 32 ? lc.a4 + (seq[i + PD] - 2) * 128 : lc.a8 + (seq[i + PD] - 34) * 256);
            if (i < 0) continue;
#pragma unroll
            for (int T = T0; T < T1; T++) {
                if (i >= NS) break;
                const int ee = seq[i] < 32 ? 2 * T - 6 - seq[i] : T + 35 - seq[i];
                if (i == 0 && T >= TC) mma_bf16(acc[T - T0], P, 0u, S, P, bq[2 * (T - TC)], bq[2 * (T - TC) + 1]);
                if (i == 1 && T >= TC) mma_bf16_k8(acc[T - T0], 0u, S, bq[20 + T - TC]);
                if (i == (T >= TC ? 2 : 0)) mma_bf16(acc[T - T0], f[19].x, 0u, f[19].y, f[19].x, bq[2 * (T - TC + 4)], bq[2 * (T - TC + 4) + 1]);
                if (seq[i] < 32 ? ee >= 0 && ee <= 9 : ee >= 10) mma_bf16(acc[T - T0], a[i % (PD + 1)][0], a[i % (PD + 1)][1], a[i % (PD + 1)][2], a[i % (PD + 1)][3], f[ee].x, f[ee].y);
            }
#pragma unroll
            for (int k = 0; k < 3; k++) {
                const int o = 256 * T0 + 512 * k;
                auto at = [&](int d) { return i - d >= 0 && i - d < NS && seq[i - d < 0 ? 0 : i - d < NS ? i - d : 0] == 2 * T0 + 4 * k - 4; };
                if (at(CV_D2)) {
                    cv_store(dq + lc.go + o, xv, yv);
                    if (layer > 19 - 2 * k) __trap();
                }
                if (at(-2)) { ldsm_x4_t(yw, lc.y + o); ldsm_x4_t(yz, lc.y + 3584 + o); }
                if (at(1)) {
#pragma unroll
                    for (int q = 0; q < 4; q++) yw[q] = add2(add2(yw[q], yz[q]), pack2(acc[2 * k + (q >> 1)][2 * (q & 1)], acc[2 * k + (q >> 1)][2 * (q & 1) + 1]));
                    stsm_x4_t(lc.y + o, yw[0], yw[1], yw[2], yw[3]);
                    xv = ldx(smem_u32(Xs) + lc.go + o);
                    __syncwarp();
                    yv = lds4(smem_u32(sm + CV_SM_Y) + c * 8192 + o + usw(lane) * 16);
                    if (layer > 20 - 2 * k) __trap();
                    if (k == 2) CST(6);
                }
            }
        }
    };
    TSTAMP1X(9, 256);
    if (threadIdx.x >= 256) {
        if (threadIdx.x < 288 && elect()) {
            mbar_init(cnt + 48, 1);
            asm volatile("fence.mbarrier_init.release.cluster;" ::: "memory");
            bulk_load(smem_u32(sm + CV_SM_T), tap + d0 * (TAPB / 16), CV_CPB * TAPB, cnt + 48);
            mbar_expect_tx(cnt + 48, CV_CPB * TAPB);
        }
        CV_IDX
        const int wgu = (warp >> 2) & 1, g = lane >> 2, ti = lane & 3;
        CST(1);
        if (warp > 8 && elect()) {
            if (warp < 15) mbar_init(cnt + 8 * (warp - 9), warp == 14 ? 8 : 4);
            else if (layer) prefetch_tmap(&tmOut);
        }
        if (warp < 13 && lane < 17 - (warp == 12)) {
            const int off = warp == 12 ? CV_SM_U : CV_SM_B + (warp == 11 ? BX_7 : (warp - 8) * BX_3), str = warp == 12 ? ULEN * 2 : BX_LEN;
#pragma unroll
            for (int c = 0; c < CV_CPB; c++) *reinterpret_cast<uint4*>(sm + off + c * str + 16 * lane) = make_uint4(0, 0, 0, 0);
        }
        fence_async_smem();
        asm volatile("bar.arrive 3, 512;" ::: "memory");
        asm volatile("bar.sync 1, 256;" ::: "memory");
        TSTAMP1X(10, 256);
        asm volatile("setmaxnreg.inc.sync.aligned.u32 168;");
        const uint32_t Tc = smem_u32(sm + CV_SM_T) + (16 + 128 * (warp & 2) + 8 * (warp & 1) + g - 2 * ti) * 4;
        uint2 fa[8][2], fn[8][2];
        auto near_taps = [&](uint2 (&f)[8][2], int c) {
#pragma unroll
            for (int m = 0; m < 16; m++) f[m >> 1][m & 1] = make_uint2(lds1v(Tc + c * TAPB + 64 * (m >> 1) - 32 * (m & 1)), lds1v(Tc + c * TAPB + 64 * (m >> 1) - 32 * (m & 1) + 512));
        };
        CST(6);
        mbar_wait(cnt + 48, 0);
        TSTAMP1X(11, 256); CST(5);
        near_taps(fa, 3 * wgu);
        near_taps(fn, 2 - wgu);
        const int hc = wgu ? warp & 3 : 4;
        const Lc lc = lane_consts(lane, hc);
        TSTAMP1X(12, 256); CST(0);
        uint32_t ya = smem_u32(sm + CV_SM_Y) + wgu * 8192 + (warp & 2) * 2048 + usw(2 * lane + (warp & 1)) * 16;
        uint64_t db = make_desc(smem_u32(Us + wgu * ULEN + UPADF), 16, 256, 3);
        if (wgu) asm volatile("bar.sync 6, 384;" ::: "memory");
        int c = wgu;
        auto chain = [&](const uint2 (&f)[8][2], auto&& meanwhile) {
            float acc[64];
            asm volatile("bar.sync %0, %1;" ::"r"(c ? 4 + wgu : 2), "r"(c ? 256 : 384) : "memory");
            TSTAMPC(1 + 3 * c);
            if (c < 2) CST(7);
            if (c == 0) fence_async_smem();
            wgmma_fence();
#pragma unroll
            for (int m = 0; m < 8; m++) {
                wgmma_rs128(acc, f[m][0], f[m][1], db - (uint64_t)(2 * m), m);
                if (m == CV_HAND && c < 4) asm volatile("bar.arrive %0, 256;" ::"r"(5 - wgu) : "memory");
            }
            wgmma_commit();
            asm volatile("griddepcontrol.launch_dependents;" ::: "memory");
            TSTAMPC(2 + 3 * c); CST(13 + (c >> 1));
            meanwhile();
            wgmma_wait<0>();
            TSTAMPC(3 + 3 * c); CST(10 + (c >> 1));
            uint32_t w[16];
#pragma unroll
            for (int j = 0; j < 16; j++) w[j] = j ? pack2(acc[4 * j] + acc[4 * j - 2], acc[4 * j + 1] + acc[4 * j - 1]) : pack2(acc[0], acc[1]);
#pragma unroll
            for (int j = 0; j < 16; j += 4) stsm_x4_t(ya + 256 * j, w[j], w[j + 1], w[j + 2], w[j + 3]);
            __syncwarp();
            if (lane == 0) mbar_arrive(cnt + 8 * c);
            c += 2; ya += 16384; db += ULEN / 4;
        };
        const uint32_t e4 = lc.e4, e8 = e4 + 428 - 4 * g;
        uint2 fl[4];
        uint32_t kk;
#pragma unroll 1
        for (;;) {
            if (c != 1) chain(fa, [&] {
                if (c == 3 || warp + c == 12) {
#pragma unroll
                    for (int k = 0; k < 19; k++) (k < 16 ? fn[(k >> 1) & 7][k & 1] : fl[k & 3]) = make_uint2(lds1(k < 10 ? e4 + 32 * k + 16 : e8 + 32 * k - 304), lds1(k < 10 ? e4 + 32 * k : e8 + 32 * k - 320));
                    fl[3] = make_uint2(lds1(lc.en), lds1(lc.en - 32));
                    kk = lds1(smem_u32(sm + CV_SM_T) + TAPB * hc + TAPE + 1672);
                }
            });
            if (c > 4) break;
            if (c == 2) { asm volatile("bar.sync 7, 384;" ::: "memory"); fence_async_smem(); }
            chain(fn, [&] { if (c == 2) near_taps(fa, 4); });
        }
        TSTAMP1X(6, 256); CST(2);
        if (wgu || warp == 8) {
            constexpr int seq[29] = {5, 6, 32, 7, 33, 8, 34, 9, 35, 10, 36, 11, 12, 13, 14, 15, 16, 17, 37, 18, 38, 19, 20, 21, 39, 22, 40, 23, 24};
            uint2 f[20];
#pragma unroll
            for (int k = 0; k < 20; k++) f[k] = k < 16 ? fn[(k >> 1) & 7][k & 1] : fl[k & 3];
            far(Int<10>(), seq, lc, hc, lane, f, kk);
        }
    } else {
        asm volatile("setmaxnreg.dec.sync.aligned.u32 88;");
        CV_IDX
        CST(5);
        const uint4* ppv = piv + tid;
        const float4* psv = sum + tid;
        const uint2* pxv = reinterpret_cast<const uint2*>(x1T + (size_t)d0 * XCP) + (tid >> 4) * 32 + (tid & 15);
        asm volatile("st.shared.u64 [%0], %1;" ::"r"(smem_u32(sm + CV_SM_O) + tid * 16), "l"((uint64_t)ppv ^ (uint64_t)psv ^ (uint64_t)pxv) : "memory");
        const int tc = (0x04302100 >> (4 * warp)) & 7;
        const Lc lc = lane_consts(lane, tc);
        pdl_sync();
        SPAN(3 + 4 * layer, 1);
        TSTAMP(0); CST(0);
        if (tid == 0) TSTAMPC(0);
        if (threadIdx.x == 0) { GSTAMP(g_tim, 15); }
        float4 sv[4];
        uint4 pv;
#pragma unroll
        for (int k = 0; k < 4; k++)
            asm volatile(CV_LD ".v4.f32 {%0,%1,%2,%3}, [%4];" : "=f"(sv[k].x), "=f"(sv[k].y), "=f"(sv[k].z), "=f"(sv[k].w) : "l"(psv + 256 * k) : "memory");
        asm volatile(CV_LD ".v4.u32 {%0,%1,%2,%3}, [%4];" : "=r"(pv.x), "=r"(pv.y), "=r"(pv.z), "=r"(pv.w) : "l"(ppv) : "memory");
        uint2 xe[CV_CPB], xo[CV_CPB];
#pragma unroll
        for (int c = 0; c < CV_NL; c++) {
            asm volatile(CV_LD ".v2.u32 {%0,%1}, [%2];" : "=r"(xe[c].x), "=r"(xe[c].y) : "l"(pxv + c * (XCP / 4)) : "memory");
            asm volatile(CV_LD ".v2.u32 {%0,%1}, [%2];" : "=r"(xo[c].x), "=r"(xo[c].y) : "l"(pxv + c * (XCP / 4) + 16) : "memory");
        }
#define CV_XD 300
#define CV_XW 0
        if (warp == CV_XW) {
            if (elect()) {
                const uint32_t c0 = clock();
                mbar_init(cnt + 56, 1);
                asm volatile("fence.mbarrier_init.release.cluster;" ::: "memory");
                mbar_expect_tx(cnt + 56, CV_CPB * 4096);
                while (clock() - c0 < CV_XD) ;
#pragma unroll
                for (int c = CV_NL; c < CV_CPB + CV_NL; c++) bulk_load(smem_u32(Xs + (c % CV_CPB) * XLEN), x1T + (size_t)(d0 + c % CV_CPB) * XCP, 4096, cnt + 56);
            }
            __syncwarp();
            CST(15);
        }
        uint32_t mw[4];
        float rs[8];
#pragma unroll
        for (int k = 0; k < 4; k++) {
            const uint32_t pw = k == 0 ? pv.x : k == 1 ? pv.y : k == 2 ? pv.z : pv.w;
            uint32_t vr;
            mw[k] = pack2(sv[k].x + __uint_as_float(pw << 16), sv[k].z + __uint_as_float(pw & 0xffff0000u));
            asm("cvt.rn.relu.bf16x2.f32 %0, %1, %2;" : "=r"(vr) : "f"(fmaf(-sv[k].z, sv[k].z, sv[k].w)), "f"(fmaf(-sv[k].x, sv[k].x, sv[k].y)));
            const uint32_t ve = pack2(__uint_as_float(vr << 16) + 1e-5f, __uint_as_float(vr & 0xffff0000u) + 1e-5f);
            const uint32_t sd = pack2(sqrt_apx(__uint_as_float(ve << 16)), sqrt_apx(__uint_as_float(ve & 0xffff0000u)));
            rs[2 * k] = rcp_apx(__uint_as_float(sd << 16)); rs[2 * k + 1] = rcp_apx(__uint_as_float(sd & 0xffff0000u));
        }
        if (rs[0] != 123.f) TSTAMP(13);
        const uint32_t ua = smem_u32(Us) + usw(tid + UPADF / 8) * 16;
        uint32_t uw[CV_CPB][4];
#pragma unroll
        for (int c = 0; c < CV_CPB; c++) {
            if (c == CV_NL) {
                if (warp == CV_XW) { mbar_wait(cnt + 56, 0); CST(7); }
                asm volatile("bar.sync 10, 256;" ::: "memory");
            }
            if (c == 1 || c == 2) {
#pragma unroll
                for (int k = c; k < (c == 1 ? 2 : CV_CPB); k++) {
 const uint4 v = ldx(smem_u32(Xs + k * XLEN) + (tid >> 4) * 256 + (tid & 15) * 8); xe[k] = make_uint2(v.x, v.y); xo[k] = make_uint2(v.z, v.w); }
            }
            const uint32_t e0 = sub2(xe[c].x, mw[0]), e1 = sub2(xe[c].y, mw[1]), o0 = sub2(xo[c].x, mw[2]), o1 = sub2(xo[c].y, mw[3]);
            uw[c][0] = pack2(__uint_as_float(e0 << 16) * rs[0], __uint_as_float(o0 << 16) * rs[4]); uw[c][1] = pack2(__uint_as_float(e0 & 0xffff0000u) * rs[1], __uint_as_float(o0 & 0xffff0000u) * rs[5]);
            uw[c][2] = pack2(__uint_as_float(e1 << 16) * rs[2], __uint_as_float(o1 << 16) * rs[6]); uw[c][3] = pack2(__uint_as_float(e1 & 0xffff0000u) * rs[3], __uint_as_float(o1 & 0xffff0000u) * rs[7]);
            asm volatile("st.shared.v4.u32 [%0], {%1,%2,%3,%4};" ::"r"(ua + c * ULEN * 2), "r"(uw[c][0]), "r"(uw[c][1]), "r"(uw[c][2]), "r"(uw[c][3]) : "memory");
            if (c < 2) {
                if (c == 1) fence_async_smem();
                asm volatile("bar.arrive %0, 384;" ::"r"(2 + 4 * c) : "memory");
                if (layer > 29 - c) __trap();
                CST(11 + c);
            }
        }
        asm volatile("bar.arrive 7, 384;" ::: "memory");
        asm volatile("bar.sync 3, 512;" ::: "memory");
        TSTAMP(1); CST(1);
        {
            auto box = [&](auto c0, auto c1, int chunk, int cb, bool full) {
                const uint32_t ea = smem_u32(Us + cb * ULEN) + usw(chunk + UPADF / 8 + (lane ? 1 : -1)) * 16, bx = smem_u32(sm + CV_SM_B + cb * BX_LEN) + chunk * 16;
                uint32_t lo[CV_CPB][4], hi[CV_CPB][2];
#pragma unroll
                for (int c = c0; c < c1; c++) {
                    lo[c][0] = 0;
#pragma unroll
                    for (int k = 1; k < 4; k++) lo[c][k] = __shfl_up_sync(~0u, uw[c][k], 1);
#pragma unroll
                    for (int k = 0; k < 2; k++) hi[c][k] = __shfl_down_sync(~0u, uw[c][k], 1);
                }
#pragma unroll
                for (int c = c0; c < c1; c++)
                    asm volatile("{\n.reg .pred p, q;\nsetp.eq.s32 p, %7, 0;\nsetp.eq.s32 q, %7, 31;\n@p ld.shared.v4.u32 {%0,%1,%2,%3}, [%6];\n@q ld.shared.v2.u32 {%4,%5}, [%6];\n}"
                                 : "+r"(lo[c][0]), "+r"(lo[c][1]), "+r"(lo[c][2]), "+r"(lo[c][3]), "+r"(hi[c][0]), "+r"(hi[c][1]) : "r"(ea + c * ULEN * 2), "r"(lane) : "memory");
#pragma unroll
                for (int c = c0; c < c1; c++) {
                    const uint32_t e[9] = {lo[c][1], lo[c][2], lo[c][3], uw[c][0], uw[c][1], uw[c][2], uw[c][3], hi[c][0], hi[c][1]};
                    uint32_t o[8], p[8], t[7], b3[5], b5[7];
#pragma unroll
                    for (int i = 0; i < 8; i++) { o[i] = __byte_perm(e[i], e[i + 1], 0x5432); p[i] = add2(e[i], o[i]); }
#pragma unroll
                    for (int i = 0; i < 5; i++) b3[i] = add2(o[i], p[i + 1]);
                    sts4(bx + c * BX_LEN + BX_3 + 160, b3);
#pragma unroll
                    for (int i = 1; i < 7; i++) { t[i] = add2(p[i], p[i + 1]); b5[i] = add2(t[i], e[i + 2]); }
                    sts4(bx + c * BX_LEN + BX_5 + 160, b5 + 2);
                    if (full) {
#pragma unroll
                        for (int i = 1; i < 5; i++) { b3[i] = add2(b3[i], t[i + 2]); t[i] = add2(t[i], b5[i + 2]); }
                        sts4(bx + c * BX_LEN + BX_7 + 272, b3 + 1);
                        sts4(bx + c * BX_LEN + BX_9 + 272, t + 1);
                    }
                }
            };
            auto reload = [&](int c, uint32_t a) { const uint4 v = lds4(a); uw[c][0] = v.x; uw[c][1] = v.y; uw[c][2] = v.z; uw[c][3] = v.w; };
            if (warp >= 6) {
#pragma unroll
                for (int c = 0; c < 3; c++) reload(c, ua - 1024 + (c + 2) * ULEN * 2);
            }
            if (warp >= 4) {
#pragma unroll
                for (int c = 3; c < 5; c++) reload(c, ua - 2048 + c * ULEN * 2);
            }
            box(Int<0>(), Int<3>(), warp < 6 ? tid : tid - 64, warp < 6 ? 0 : 2, warp < 4);
            if (warp >= 4) box(Int<3>(), Int<5>(), tid - 128, 0, true);
            else if (tid >= 128 - CV_CPB) {
                const int c = 127 - tid;
                const uint2 v = *reinterpret_cast<const uint2*>(Us + c * ULEN + UPADF);
                const float s1 = __uint_as_float(v.x << 16), s2 = s1 + __uint_as_float(v.x & 0xffff0000u), s3 = s2 + __uint_as_float(v.y << 16), s4 = s3 + __uint_as_float(v.y & 0xffff0000u);
                unsigned char* bc = sm + CV_SM_B + c * BX_LEN;
                *reinterpret_cast<uint32_t*>(bc + BX_5 + 156) = pack2(s1, s2);
                *reinterpret_cast<uint2*>(bc + BX_7 + 264) = make_uint2(v.x << 16, pack2(s2, s3));
                *reinterpret_cast<uint2*>(bc + BX_9 + 264) = make_uint2(pack2(s1, s2), pack2(s3, s4));
            }
        }
        __syncwarp();
        if (lane == 0) mbar_arrive(cnt + 40);
        TSTAMP(2); CST(2);
        if (layer && blockIdx.x == 0 && tid == 224) g_epoch = ld_epoch();
        __syncwarp();
        if ((0x6e >> warp) & 1) {
            constexpr int seq[16] = {0, 1, 2, 3, 4, 5, 6, 32, 7, 8, 9, 33, 10, 34, 11, 12};
            uint2 f[20];
            mbar_wait(cnt, 0);
            const uint32_t e8 = lc.e4 + 428 - (lane & 28);
#pragma unroll
            for (int k = 0; k < 13; k++) f[k] = make_uint2(lds1(k < 10 ? lc.e4 + 32 * k + 16 : e8 + 32 * k - 304), lds1(k < 10 ? lc.e4 + 32 * k : e8 + 32 * k - 320));
            f[19] = make_uint2(lds1(lc.en), lds1(lc.en - 32));
            far(Int<4>(), seq, lc, tc, lane, f, lds1(smem_u32(sm + CV_SM_T) + TAPB * tc + TAPE + 1672));
        }
    }
    {
        CV_IDX
        if ((0xc91 >> warp) & 1) {
            const int c = __popc(0xc91 & ((1 << warp) - 1));
            uint4 xv[2], yv[2];
#pragma unroll
            for (int k = 0; k < 2; k++) xv[k] = ldx(smem_u32(Xs + c * XLEN) + 512 * k + (lane >> 4) * 256 + (lane & 15) * 8);
            const uint32_t u0 = lds1(smem_u32(Us + c * ULEN) + (lane == 31 ? UPADF * 2 : 0));
            mbar_wait(cnt + 8 * c, 0);
#pragma unroll
            for (int k = 0; k < 2; k++) yv[k] = lds4(smem_u32(sm + CV_SM_Y) + c * 8192 + 512 * k + usw(lane) * 16);
            const uint4 yz = lds4(smem_u32(sm + CV_SM_Y) + c * 8192 + 4096 + usw(lane) * 16);
            const float kk = __uint_as_float(lds1(smem_u32(sm + CV_SM_T) + TAPB * c + TAPE + 1272) << 16);
            yv[1].x = add2(yv[1].x, yz.x); yv[1].y = add2(yv[1].y, yz.y); yv[1].z = add2(yv[1].z, yz.z);
            yv[1].w = pack2(fmaf(kk, __uint_as_float(u0 << 16), __uint_as_float(yv[1].w << 16) + __uint_as_float(yz.w << 16)),
                            fmaf(kk, __uint_as_float(u0 << 16) + __uint_as_float(u0 & 0xffff0000u), __uint_as_float(yv[1].w & 0xffff0000u) + __uint_as_float(yz.w & 0xffff0000u)));
#pragma unroll
            for (int k = 0; k < 2; k++) cv_store(dq + c * XCP * 2 + (lane >> 4) * 256 + (lane & 15) * 8 + 512 * k, xv[k], yv[k]);
        }
        TSTAMP(4); CST(8);
        if (layer == 1) {
            const int rb = (blockIdx.x >> 3) + (warp & 8) * 2, cg = blockIdx.x & 7, ch = (tid >> 3) & 31;
            const bf16* src = dst + (size_t)(cg * 80 + ch) * XCP + rb * 64 + (tid & 7) * 8;
            uint32_t v[3][4];
            __syncthreads();
            pause(warp & 8 ? CV_TD1 : CV_TD0);
            uint32_t todo = (warp & 4) ? 3 : 7;
#pragma unroll 1
            for (int it = 0; it < SPIN_MAX; it++) {
#pragma unroll
                for (int k = 0; k < 3; k++)
                    if (todo >> k & 1)
                        asm volatile("ld.relaxed.gpu.global.v4.u32 {%0,%1,%2,%3}, [%4];" : "=r"(v[k][0]), "=r"(v[k][1]), "=r"(v[k][2]), "=r"(v[k][3]) : "l"(src + k * (32 * XCP)) : "memory");
#pragma unroll
                for (int k = 0; k < 3; k++)
                    if ((todo >> k & 1) && v[k][0] != ~0u && v[k][1] != ~0u && v[k][2] != ~0u && v[k][3] != ~0u) {
                        *reinterpret_cast<uint4*>(sm + (32 * k + ch) * 272 + ((tid & 7) + (warp & 8)) * 16) = make_uint4(v[k][0], v[k][1], v[k][2], v[k][3]);
                        todo ^= 1u << k;
                    }
                if (!todo) break;
                __nanosleep(CV_SLEEP);
            }
            __syncwarp();
            asm volatile("bar.sync %0, 256;" ::"r"(8 + (warp >> 3)) : "memory");
            uint32_t w[12];
#pragma unroll
            for (int k = 0; k < 3; k++) ldsm_x4(&w[4 * k], smem_u32(sm) + min(32 * k + lane, 79) * 272 + warp * 16);
            const uint32_t ot = smem_u32(sm + CV_SM_O) + warp * 1280, oa = ot + (lane & 7) * 160 + (lane >> 3) * 16;
            stsm_x4_t(oa, w[0], w[1], w[2], w[3]);
            stsm_x4_t(oa + 64, w[4], w[5], w[6], w[7]);
            asm volatile("stmatrix.sync.aligned.m8n8.x2.trans.shared.b16 [%0], {%1,%2};" ::"r"(oa + 128), "r"(w[8]), "r"(w[9]) : "memory");
            fence_async_smem();
            __syncwarp();
            if (lane == 0) {
                asm volatile("cp.async.bulk.tensor.3d.global.shared::cta.bulk_group [%0, {%1, %2, %3}], [%4];" ::"l"(&tmOut), "r"(cg * 80), "r"((rb >> 1) * 64 + 8 * (warp & 7)), "r"(rb & 1), "r"(ot) : "memory");
                asm volatile("cp.async.bulk.commit_group;" ::: "memory");
                asm volatile("cp.async.bulk.wait_group.read 0;" ::: "memory");
            }
        }
    }
    TSTAMP(3); CST(9); CST_END;
    GSTAMP(g_tim, 14);
    SPAN(3 + 4 * layer, 3);
}

template <int TA, int TB>
__device__ __forceinline__ void wgmma_n240(float (&d)[120], uint64_t da, uint64_t db, int acc) {
    asm volatile("{\n.reg .pred p;\nsetp.ne.b32 p, %124, 0;\nwgmma.mma_async.sync.aligned.m64n240k16.f32.bf16.bf16 {%0,%1,%2,%3,%4,%5,%6,%7,%8,%9,%10,%11,%12,%13,%14,%15,%16,%17,%18,%19,%20,%21,%22,%23,%24,%25,%26,%27,%28,%29,%30,%31,%32,%33,%34,%35,%36,%37,%38,%39,%40,%41,%42,%43,%44,%45,%46,%47,%48,%49,%50,%51,%52,%53,%54,%55,%56,%57,%58,%59,%60,%61,%62,%63,%64,%65,%66,%67,%68,%69,%70,%71,%72,%73,%74,%75,%76,%77,%78,%79,%80,%81,%82,%83,%84,%85,%86,%87,%88,%89,%90,%91,%92,%93,%94,%95,%96,%97,%98,%99,%100,%101,%102,%103,%104,%105,%106,%107,%108,%109,%110,%111,%112,%113,%114,%115,%116,%117,%118,%119}, %120, %121, p, 1, 1, %122, %123;\n}"
                 : "+f"(d[0]), "+f"(d[1]), "+f"(d[2]), "+f"(d[3]), "+f"(d[4]), "+f"(d[5]), "+f"(d[6]), "+f"(d[7]), "+f"(d[8]), "+f"(d[9]), "+f"(d[10]), "+f"(d[11]), "+f"(d[12]), "+f"(d[13]), "+f"(d[14]), "+f"(d[15]), "+f"(d[16]), "+f"(d[17]), "+f"(d[18]), "+f"(d[19]), "+f"(d[20]), "+f"(d[21]), "+f"(d[22]), "+f"(d[23]), "+f"(d[24]), "+f"(d[25]), "+f"(d[26]), "+f"(d[27]), "+f"(d[28]), "+f"(d[29]), "+f"(d[30]), "+f"(d[31]), "+f"(d[32]), "+f"(d[33]), "+f"(d[34]), "+f"(d[35]), "+f"(d[36]), "+f"(d[37]), "+f"(d[38]), "+f"(d[39]), "+f"(d[40]), "+f"(d[41]), "+f"(d[42]), "+f"(d[43]), "+f"(d[44]), "+f"(d[45]), "+f"(d[46]), "+f"(d[47]), "+f"(d[48]), "+f"(d[49]), "+f"(d[50]), "+f"(d[51]), "+f"(d[52]), "+f"(d[53]), "+f"(d[54]), "+f"(d[55]), "+f"(d[56]), "+f"(d[57]), "+f"(d[58]), "+f"(d[59]), "+f"(d[60]), "+f"(d[61]), "+f"(d[62]), "+f"(d[63]), "+f"(d[64]), "+f"(d[65]), "+f"(d[66]), "+f"(d[67]), "+f"(d[68]), "+f"(d[69]), "+f"(d[70]), "+f"(d[71]), "+f"(d[72]), "+f"(d[73]), "+f"(d[74]), "+f"(d[75]), "+f"(d[76]), "+f"(d[77]), "+f"(d[78]), "+f"(d[79]), "+f"(d[80]), "+f"(d[81]), "+f"(d[82]), "+f"(d[83]), "+f"(d[84]), "+f"(d[85]), "+f"(d[86]), "+f"(d[87]), "+f"(d[88]), "+f"(d[89]), "+f"(d[90]), "+f"(d[91]), "+f"(d[92]), "+f"(d[93]), "+f"(d[94]), "+f"(d[95]), "+f"(d[96]), "+f"(d[97]), "+f"(d[98]), "+f"(d[99]), "+f"(d[100]), "+f"(d[101]), "+f"(d[102]), "+f"(d[103]), "+f"(d[104]), "+f"(d[105]), "+f"(d[106]), "+f"(d[107]), "+f"(d[108]), "+f"(d[109]), "+f"(d[110]), "+f"(d[111]), "+f"(d[112]), "+f"(d[113]), "+f"(d[114]), "+f"(d[115]), "+f"(d[116]), "+f"(d[117]), "+f"(d[118]), "+f"(d[119])
                 : "l"(da), "l"(db), "n"(TA), "n"(TB), "r"(acc));
}

__device__ __forceinline__ void wgmma_n80(float (&d)[40], uint64_t da, uint64_t db, int acc) {
    asm volatile("{\n.reg .pred p;\nsetp.ne.b32 p, %42, 0;\nwgmma.mma_async.sync.aligned.m64n80k16.f32.bf16.bf16 {%0,%1,%2,%3,%4,%5,%6,%7,%8,%9,%10,%11,%12,%13,%14,%15,%16,%17,%18,%19,%20,%21,%22,%23,%24,%25,%26,%27,%28,%29,%30,%31,%32,%33,%34,%35,%36,%37,%38,%39}, %40, %41, p, 1, 1, 0, 1;\n}"
                 : "+f"(d[0]), "+f"(d[1]), "+f"(d[2]), "+f"(d[3]), "+f"(d[4]), "+f"(d[5]), "+f"(d[6]), "+f"(d[7]), "+f"(d[8]), "+f"(d[9]), "+f"(d[10]), "+f"(d[11]), "+f"(d[12]), "+f"(d[13]), "+f"(d[14]), "+f"(d[15]), "+f"(d[16]), "+f"(d[17]), "+f"(d[18]), "+f"(d[19]), "+f"(d[20]), "+f"(d[21]), "+f"(d[22]), "+f"(d[23]), "+f"(d[24]), "+f"(d[25]), "+f"(d[26]), "+f"(d[27]), "+f"(d[28]), "+f"(d[29]), "+f"(d[30]), "+f"(d[31]), "+f"(d[32]), "+f"(d[33]), "+f"(d[34]), "+f"(d[35]), "+f"(d[36]), "+f"(d[37]), "+f"(d[38]), "+f"(d[39])
                 : "l"(da), "l"(db), "r"(acc));
}

constexpr int A1_THREADS = 384;
constexpr int A1_NST = 4;
#define A1_SKEW 8
constexpr int A1_STAGE = 16384 + WQ_STAGE;
constexpr int A1_KVP = 336;
constexpr int A1_SM_KV = 2 * A1_STAGE;
constexpr int A1_SM_END = A1_NST * A1_STAGE;
constexpr int A1_SM_BAR = A1_SM_END + 3072 + 3 * WOB + 64;
constexpr int A1_SM_RS = A1_SM_END + 512;
constexpr int A1_SM_W0 = A1_SM_END + 3072, A1_SM_W3 = A1_SM_END - 3 * WOB, A1_SM_A1 = 2 * WOB, A1_SM_A0 = A1_SM_A1 + 61440;
constexpr int A1_SM_XA = A1_SM_W0 + 2 * WOB, A1_SM_XB = A1_SM_XA + 2048;
constexpr int A1_SMEM = A1_SM_BAR + 512 + 7 * CST_EXTRA / 4;
static_assert(A1_SM_W3 >= A1_SM_KV + 144 * A1_KVP && A1_SM_W3 % 512 == 0 && A1_SM_A1 % 1024 == 0 && A1_SM_A0 <= A1_SM_KV && A1_SM_A0 + 61440 <= A1_SM_W3 && A1_SMEM <= 232448 && 11 * 4096 <= A1_STAGE, "layout");
__device__ __forceinline__ constexpr uint32_t wo_off(int h) { return h * WOB + (h < 3 ? A1_SM_W0 : h < 6 ? A1_SM_W3 - 3 * WOB : -6 * WOB); }
#define A1_FRED "red.relaxed.gpu.global.add.u32"
#define A1_FLD "ld.relaxed.gpu.global.u32"
#define ST_SLEEP 20
#define ST_SLEEP0 300
#define A1_P0 2
#define A1_PW (kb - 2)
#define A1_FSPIN SPIN_MAX
#define A1_FSLEEP 40
#define YT_LAYER 1
#define WOT 11
#define A1_P1 550
#define A1_P2 300
#define A1_WOAT 6

template <int L>
__device__ __forceinline__ void a1_mainloop(float (&acc)[120], uint32_t sbase, uint32_t bars, int wg, int tile) {
    constexpr int layer = L; (void)layer;
    const uint64_t da0 = L ? make_desc(sbase + wg * 8192, 8192, 1024, 1) : make_desc(sbase + wg * 8192, 16, 1024, 1), db0 = make_desc(sbase + 16384, 1024, 256, 3);
#pragma unroll 1
    for (int t = 0;; t++) {
        const int st = t % A1_NST;
        mbar_wait(bars + 8 * st, (t / A1_NST) & 1);
        if (t == A1_SKEW && wg == 0) mbar_wait(bars + 160, 0);
        TSTAMP3(1 + t);
        if (t == 0) CSA(0);
        wgmma_fence();
#pragma unroll
        for (int kk = 0; kk < 4; kk++) wgmma_n240<L, 1>(acc, da0 + (uint32_t)(st * (A1_STAGE / 16) + kk * (L ? 128 : 2)), db0 + (uint32_t)(st * (A1_STAGE / 16) + (kk >> 1) * (WQ_STAGE / 32) + (kk & 1) * 32), kk ? 1 : t);
        wgmma_commit();
        if (t == 9) break;
        if (t == A1_SKEW - 1 && wg == 0) wgmma_wait<0>(); else wgmma_wait<1>();
        if (t > 0 && (threadIdx.x & 127) == 0) {
            if (t != A1_SKEW || wg) mbar_arrive(bars + 8 * (A1_NST + (t - 1) % A1_NST));
            if (t == A1_SKEW - 1 && wg == 0) mbar_arrive(bars + 8 * (A1_NST + t % A1_NST));
        }
    }
}

template <bool MAP>
__global__ void __launch_bounds__(A1_THREADS, 1) a1_kernel(const __grid_constant__ Par in, const __grid_constant__ CUtensorMap tmX, const __grid_constant__ CUtensorMap tmR,
                                                           const __grid_constant__ CUtensorMap tmX1, const __grid_constant__ KgMaps tmW, const __grid_constant__ TileTab tab) {
#define layer in.layer
    const unsigned char* const wo = reinterpret_cast<const unsigned char*>(in.wop);
    float2* const rsum = reinterpret_cast<float2*>(in.sum);
    uint4* const of = in.of;
    extern __shared__ __align__(1024) unsigned char stg[];
    const uint32_t sbase = smem_u32(stg);
    const uint32_t bars = sbase + A1_SM_BAR;
    const uint32_t bar_stat = bars + 64, bar_kv = bars + 72, bar_rd = bars + 168;
    const uint32_t bar_wo = bars + 208, bar_done = bars + 216, bar_pv = bars + 224, bar_kvf = bars + 232, bar_f2 = bars + 248, bar_e2 = bars + 384, que = bars + 448;
    const int tid = threadIdx.x;
    CSK(0);
    const int w = __shfl_sync(~0u, tid >> 5, 0), wg = w >> 2;
    uint32_t smid;
    asm volatile("mov.u32 %0, %smid;" : "=r"(smid));
    const uint4 tv = tab.e[(MAP ? smid : blockIdx.x) + (tid & (smid >> 12))];
    const uint64_t pa = reinterpret_cast<const uint64_t*>(&in)[tid & (smid >> 12)], pb = reinterpret_cast<const uint64_t*>(&in)[6 + (tid & (smid >> 12))];
    const bool one = elect();
    uint32_t tz;
    const unsigned char* wq;
    auto entry = [&] { tz = __shfl_sync(~0u, tv.z, 0); wq = (const unsigned char*)(((uint64_t)__shfl_sync(~0u, tv.y, 0) << 32) | __shfl_sync(~0u, tv.x, 0)); };
    auto issue_w = [&](unsigned it) { bulk_load(sbase + (it % A1_NST) * A1_STAGE + 16384, wq + it * WQ_STAGE, WQ_STAGE, bars + 8 * (it % A1_NST)); };
    auto issue_x = [&](unsigned it, int kb) {
        asm volatile("cp.async.bulk.tensor.5d.shared::cluster.global.mbarrier::complete_tx::bytes [%0], [%1, {%3, %3, %3, %4, %5}], [%2];"
                     ::"r"(sbase + (it % A1_NST) * A1_STAGE), "l"(&tmX), "r"(bars + 8 * (it % A1_NST)), "r"(0), "r"(tz & 15), "r"(kb) : "memory");
    };
    auto first_x = [&] {
        issue_x(0, (tz >> 16) & 7); issue_x(1, ((tz >> 16) & 7) + 1);
    };
    auto expect = [&] {
#pragma unroll
        for (int i = 0; i < A1_NST; i++) mbar_expect_tx(bars + 8 * i, A1_STAGE);
    };
    if (w == 8) {
        if (one) {
            prefetch_tmap(&tmX); prefetch_tmap(&tmW.q);
#pragma unroll
            for (int i = 0; i < A1_NST; i++) mbar_init(bars + 8 * i, 1);
            asm volatile("fence.mbarrier_init.release.cluster;" ::: "memory");
        }
        __syncwarp();
        asm volatile("bar.arrive 0, 384;" ::: "memory");
        if (smid >> 12) __trap();
        entry();
        if ((tz & 0x80000010u) == 16) {
            if (one) {
                issue_w(0);
                asm volatile("griddepcontrol.wait;" ::: "memory");
                issue_x(0, (tz >> 16) & 7);
                expect();
                pause(A1_P1);
                issue_w(1);
                issue_x(1, ((tz >> 16) & 7) + 1);
                asm volatile("griddepcontrol.launch_dependents;" ::: "memory");
            }
#pragma unroll
            for (int kb = 2; kb < A1_NST; kb++) {
                __syncwarp();
                mbar_wait(bars + 8 * (kb - 2), 0);
                if (kb == 2) pause(A1_P2);
                if (one) { issue_x(kb, ((tz >> 16) & 7) + kb); issue_w(kb); }
                CSK(6 + kb);
            }
        }
        __syncwarp();
        if (!(tz & 16) && blockIdx.x < 128) kgen_first(in, tmW, sbase + A1_SM_W0, bars - 24, one);
        __syncwarp();
    }
    if (w > 8) CSK(8);
    const bool gen = w != 8 && in.logA && blockIdx.x < 128;
    KgPar kp;
    const int w11 = w < 8 ? 2 * (w & 3) + (w >> 2) : w - 1;
    if (gen) kgen_load(in, reinterpret_cast<const bf16*>(pa), w11, kp);
    if (w > 8) CSK(9);
    if (w == 8) {
        const int tile = tz >> 24, mb = tz & 15, hg = (tz >> 8) & 7, kb0 = (tz >> 16) & 7;
        const unsigned l1 = (tz >> 4) & 1;
        if (__builtin_expect(!l1, 0)) {
            CSK(1);
            const uint32_t ep = ld_epoch();
            if (one) {
                kgen_side(in, sbase + A1_SM_W0, bars - 24);
                if (tile < 128) { first_x(); expect(); }
                asm volatile("cp.async.bulk.wait_group 0;" ::: "memory");
            }
            __syncwarp();
            asm volatile("bar.arrive 10, 96;" ::: "memory");
            CSK(6);
            if (tile < 128) {
                await_all(96 + 32 * hg, ep * 15);
                if (one) issue_w(0);
                __syncwarp();
                mbar_wait(bars, 0);
                if (one) { issue_w(1); issue_x(2, kb0 + 2); issue_w(2); }
            }
            CSK(7);
            asm volatile("bar.sync 3, 384;" ::: "memory");
            if (tile < 128 && one) {
                fence_async_smem();
                issue_x(3, kb0 + 3); issue_w(3);
                mbar_expect_tx(bars + 240, 20480);
                bulk_load(sbase + A1_SM_W0, in.x + (size_t)(mb * 128 + hg * 16) * DM, 20480, bars + 240);
            }
            __syncwarp();
            CSK(9);
        } else asm volatile("bar.sync 3, 64;" ::: "memory");
        if (tile < 128 && elect()) {
#pragma unroll 1
            for (unsigned kb = A1_NST; kb < 10; kb++) {
                mbar_wait(bars + 8 * (A1_NST + kb % A1_NST), ((kb / A1_NST) - 1) & 1);
                if (l1 && kb < 9) mbar_wait(bar_rd + 8 * (kb - A1_NST), 0);
                mbar_expect_tx(bars + 8 * (kb % A1_NST), A1_STAGE);
                issue_x(kb, kb < 5 ? kb + kb0 : kb - kb0); issue_w(kb);
                if (kb == (l1 ? A1_WOAT : 9)) {
                    if (!l1) { mbar_wait(bar_stat, 0); asm volatile("fence.proxy.async.global;" ::: "memory"); }
                    mbar_expect_tx(bar_wo, 8 * WOB);
                    bulk_load(sbase + A1_SM_W0, wo + hg * 8 * WOB, 2 * WOB, bar_wo);
                }
            }
            mbar_wait(bars + 8 * (A1_NST + 3), 1);
            bulk_load(sbase + A1_SM_W3, wo + (hg * 8 + 3) * WOB, 3 * WOB, bar_wo);
        }
        CSA(4); CSA_END;
        return;
    }
    {
        if (w < 8 && one) {
#pragma unroll 1
            for (uint32_t c = (w & 4 ? w & 2 ? 0x1111112'01111111ull : 0x1111111'01111184ull : w & 2 ? 0x3122222'01111111ull : 0x1111132'02220000ull) >> (32 * (w & 1)), b = bars + 56 * w; c; c >>= 4, b += 8)
                if (c & 15) mbar_init(b, c & 15);
            asm volatile("fence.mbarrier_init.release.cluster;" ::: "memory");
        }
        __syncwarp();
        asm volatile("bar.sync 0, 384;" ::: "memory");
        if (layer) {
            if (w == 9) asm volatile("bar.arrive 3, 64;" ::: "memory");
        } else {
            if (gen) { SPAN(0, 0); SPAN(0, 1); kgen_tables(in, reinterpret_cast<uint4*>(stg + 3 * A1_STAGE), w11, kp); }
            else if (w != 11 && w11 > 1) asm volatile("bar.arrive 9, 352;" ::: "memory");
            __syncwarp();
            if (w11 < 2) {
                asm volatile("bar.sync 10, 96;" ::: "memory");
                kgen_sums(in, sbase + A1_SM_W0, w11);
                __syncwarp();
                asm volatile("bar.arrive 9, 352;" ::: "memory");
                CSK(1);
            }
            if (w == 9) asm volatile("bar.sync 3, 384;" ::: "memory"); else asm volatile("bar.arrive 3, 384;" ::: "memory");
        }
    }
    tz = __shfl_sync(~0u, tv.z + (uint32_t)(pb >> 32), 0);
    const int tile = tz >> 24, mb = tz & 15, hg = (tz >> 8) & 7;
    float2* rst = reinterpret_cast<float2*>(stg + A1_SM_RS) + 8;
    if (wg == 2) {
        if (w == 11 && layer == 0) {
            asm volatile("bar.sync 9, 352;" ::: "memory");
            CSK(5);
            if (one) publish(64);
            __syncwarp();
            CSK(6);
        }
        if (tile >= 128) { sm_idle(layer); return; }
        if (w == 10) {
            if (one) { prefetch_tmap(&tmR); prefetch_tmap(&tmX1); }
            uint32_t ns;
            asm volatile("mov.u32 %0, %nsmid;" : "=r"(ns));
            if (MAP && ns != 132) __trap();
        }
        __syncwarp();
        if (w == 9) {
            if (layer && one) {
                mbar_expect_tx(bar_stat, 3840);
                bulk_load(sbase + A1_SM_XB, g_xb + tile * 240, 3840, bar_stat);
            }
            __syncwarp();
#pragma unroll 1
            for (int it = 0; it < 4096 * layer; it++) {
                uint32_t ok;
                asm volatile("{\n.reg .pred p;\nmbarrier.try_wait.parity.shared::cta.b64 p, [%1], %2;\nselp.b32 %0, 1, 0, p;\n}" : "=r"(ok) : "r"(bars + 8), "n"(0) : "memory");
                if (__any_sync(~0u, ok)) break;
            }
            uint4* pre = of + (mb * 8 + hg) * 1280 + (tid - 288);
#pragma unroll 1
            for (int k = 0; k < 5 + 5 * layer; k++) {
#pragma unroll
                for (int i = 0; i < 8; i++) asm volatile("st.global.v4.u32 [%0], {%1,%1,%1,%1};" ::"l"(pre + 32 * i), "r"(~0u) : "memory");
                pre += k < 5 ? 256 : XCP / 8;
                if (layer) pause(400);
                if (k == 4) {
                    CSA(2);
                    asm volatile("fence.acq_rel.gpu;" ::: "memory");
                    asm volatile("fence.proxy.async.global;" ::: "memory");
                    __syncwarp();
                    if (tid == 288) mbar_arrive(bar_done);
                    CSA(3);
                    pre = reinterpret_cast<uint4*>(g_yT) + tile * (5 * XCP / 8) + (tid - 288);
                }
            }
            if (layer == 0) {
                asm volatile("griddepcontrol.launch_dependents;" ::: "memory");
                await_all(64, ld_epoch() * gridDim.x);
                CSA(5);
                float4 a[2] = {};
#pragma unroll
                for (int k = 0; k < 10; k++)
#pragma unroll
                    for (int h = 0; h < 2; h++) {
                        const int c4 = min(tid - 288 + 32 * h, 59);
                        const float4 v = __ldcg(reinterpret_cast<const float4*>(g_csp + (k / 5) * 9600 + (k % 5) * 640 + hg * 80) + c4 + (c4 / 20) * 780);
                        a[h].x += v.x; a[h].y += v.y; a[h].z += v.z; a[h].w += v.w;
                    }
#pragma unroll
                for (int h = 0; h < 2; h++)
#pragma unroll
                    for (int k = 0; k < 4; k++) {
                        const float c = 0.5f * (k == 0 ? a[h].x : k == 1 ? a[h].y : k == 2 ? a[h].z : a[h].w), c1 = c - rbf(c), c2 = c1 - rbf(c1);
                        *reinterpret_cast<uint4*>(stg + A1_SM_XB + (4 * min(tid - 288 + 32 * h, 59) + k) * 16) = make_uint4(pack2(c, c1), pack2(c2, 0.f), 0u, 0u);
                    }
                fence_async_smem();
                __syncwarp();
                if (one) {
                    bulk_store(g_xb + tile * 240, sbase + A1_SM_XB, 3840);
                    asm volatile("cp.async.bulk.commit_group;" ::: "memory");
                    asm volatile("cp.async.bulk.wait_group.read 0;" ::: "memory");
                    mbar_arrive(bar_stat);
                }
                __syncwarp();
                CSA(1);
            }
            TSTAMP1T(9, 288);
        } else {
            const int j = tid - 320;
            const uint32_t tag = ld_epoch();
            if (tid == 352) sm_started(layer);
            const int ch = j & 7, kg = (j >> 3) & 3;
            const unsigned char* src = stg + (layer ? (j >> 5) * 8192 + (hg & 3) * 2048 : A1_SM_W0 + (j >> 2) * 1280);
            const int of0 = layer ? kg * 128 + ((ch ^ kg) << 4) : (j & 7) << 4, ofx = layer ? 576 : 64, ofy = layer ? 1024 : 128;
            float s[8], q[8], p0[8];
#pragma unroll
            for (int i = 0; i < 8; i++) { s[i] = 0.f; q[i] = 0.f; }
#pragma unroll 1
            for (int it = 0; it < 5; it++) {
                uint4 v[4];
                mbar_wait(layer ? bars + 8 * (it % A1_NST) : bars + 240, layer * it / A1_NST);
#pragma unroll
                for (int k = 0; k < 4; k++) v[k] = *reinterpret_cast<const uint4*>(src + (layer ? (it % A1_NST) * A1_STAGE : it * 256) + (k & 1 ? of0 ^ ofx : of0) + (k >> 1) * ofy);
                if (it == 0) {
                    const uint4 pv = *reinterpret_cast<const uint4*>(src + (layer ? ch << 4 : 0));
                    const uint32_t w[4] = {pv.x, pv.y, pv.z, pv.w};
#pragma unroll
                    for (int i = 0; i < 4; i++) { p0[2 * i] = __uint_as_float((layer ? w[i] : w[0]) << 16); p0[2 * i + 1] = __uint_as_float(layer ? w[i] & 0xffff0000u : w[0] << 16); }
                }
                asm volatile("" :: "r"(v[0].x), "r"(v[1].x), "r"(v[2].x), "r"(v[3].x), "f"(p0[0]) : "memory");
                __syncwarp();
                if ((tid & 31) == 0) mbar_arrive(bar_rd + 8 * it);
#pragma unroll
                for (int k = 0; k < 4; k++) {
                    const uint32_t w[4] = {v[k].x, v[k].y, v[k].z, v[k].w};
#pragma unroll
                    for (int i = 0; i < 4; i++) {
                        const float a = __uint_as_float(w[i] << 16) - p0[2 * i], b = __uint_as_float(w[i] & 0xffff0000u) - p0[2 * i + 1];
                        s[2 * i] += a; s[2 * i + 1] += b; q[2 * i] = fmaf(a, a, q[2 * i]); q[2 * i + 1] = fmaf(b, b, q[2 * i + 1]);
                    }
                }
            }
            float o[4];
            int row;
            if (layer == 0) {
                float s0 = ((s[0] + s[1]) + (s[2] + s[3])) + ((s[4] + s[5]) + (s[6] + s[7])), q0 = ((q[0] + q[1]) + (q[2] + q[3])) + ((q[4] + q[5]) + (q[6] + q[7]));
#pragma unroll
                for (int o = 1; o <= 2; o <<= 1) { s0 += __shfl_xor_sync(~0u, s0, o); q0 += __shfl_xor_sync(~0u, q0, o); }
                if ((j & 3) == 0) {
                    const float d = s0 * (1.0f / DM);
                    const uint32_t ms = pack2(p0[0] + d, sqrt_apx(rbf(rbf(fmaxf(fmaf(-d, d, q0 * (1.0f / DM)), 0.f)) + 1e-5f)));
                    asm volatile("st.global.cg.u64 [%0], %1;" ::"l"(g_rstat + mb * 128 + (j & 4) * 16 + hg * 8 + (j >> 3)), "l"(tagw(ms, tag)) : "memory");
                    g_piv[mb * 128 + hg * 16 + ((j >> 2) & 8) + (j & 4) + ((j >> 3) & 3)] = __ushort_as_bfloat16((unsigned short)ms);
                }
                ulonglong2 v;
#pragma unroll 1
                for (int it = 0; it < SPIN_MAX; it++) {
                    v = ld_tag2(reinterpret_cast<const ulonglong2*>(g_rstat + mb * 128) + j);
                    if (__all_sync(~0u, tag_ok(v, tag))) break;
                    __nanosleep(100);
                }
                o[0] = __uint_as_float((uint32_t)v.x << 16); o[1] = rcp_apx(__uint_as_float((uint32_t)v.x & 0xffff0000u));
                o[2] = __uint_as_float((uint32_t)v.y << 16); o[3] = rcp_apx(__uint_as_float((uint32_t)v.y & 0xffff0000u));
                row = 2 * j;
            } else {
#pragma unroll
                for (int i = 0; i < 4; i++) {
                    const bool up = kg & 2;
                    const float ss = __shfl_xor_sync(~0u, up ? s[i] : s[i + 4], 16), qq = __shfl_xor_sync(~0u, up ? q[i] : q[i + 4], 16);
                    s[i] = (up ? s[i + 4] : s[i]) + ss; q[i] = (up ? q[i + 4] : q[i]) + qq; p0[i] = up ? p0[i + 4] : p0[i];
                }
#pragma unroll
                for (int i = 0; i < 2; i++) {
                    const bool up = kg & 1;
                    const float ss = __shfl_xor_sync(~0u, up ? s[i] : s[i + 2], 8), qq = __shfl_xor_sync(~0u, up ? q[i] : q[i + 2], 8);
                    s[i] = (up ? s[i + 2] : s[i]) + ss; q[i] = (up ? q[i + 2] : q[i]) + qq; p0[i] = up ? p0[i + 2] : p0[i];
                }
                uint4* gp = g_halo + 86016 + mb * 512 + j;
                const float d0 = s[0] * (1.0f / 80.0f), d1 = s[1] * (1.0f / 80.0f);
                asm volatile("st.relaxed.gpu.global.v4.f32 [%0], {%1,%2,%3,%4};" ::"l"(gp + hg * 64), "f"(p0[0] + d0), "f"(fmaxf(fmaf(-d0, s[0], q[0]), 0.f)), "f"(p0[1] + d1), "f"(fmaxf(fmaf(-d1, s[1], q[1]), 0.f)) : "memory");
                __nanosleep(ST_SLEEP0);
                uint32_t pw[8][4], todo = 0xff;
#pragma unroll 1
                for (int it = 0; it < SPIN_MAX; it++) {
#pragma unroll
                    for (int k = 0; k < 8; k++)
                        if (todo >> k & 1) asm volatile("ld.relaxed.gpu.global.v4.u32 {%0,%1,%2,%3}, [%4];" : "=r"(pw[k][0]), "=r"(pw[k][1]), "=r"(pw[k][2]), "=r"(pw[k][3]) : "l"(gp + k * 64) : "memory");
#pragma unroll
                    for (int k = 0; k < 8; k++)
                        if (__all_sync(~0u, pw[k][0] != ~0u && pw[k][1] != ~0u && pw[k][2] != ~0u && pw[k][3] != ~0u)) todo &= ~(1u << k);
                    if (!todo) break;
                    __nanosleep(ST_SLEEP);
                }
#pragma unroll
                for (int r = 0; r < 2; r++) {
                    float mean = 0.f, m2 = 0.f;
#pragma unroll
                    for (int k = 0; k < 8; k++) mean += __uint_as_float(pw[k][2 * r]);
                    mean *= 0.125f;
#pragma unroll
                    for (int k = 0; k < 8; k++) {
                        const float dm = __uint_as_float(pw[k][2 * r]) - mean;
                        m2 += fmaf(80.0f * dm, dm, __uint_as_float(pw[k][2 * r + 1]));
                    }
                    o[2 * r] = rbf(mean);
                    o[2 * r + 1] = rcp_apx(rbf(sqrt_apx(rbf(rbf(m2 * (1.0f / DM)) + 1e-5f))));
                }
                row = (j >> 5) * 64 + (j & 7) * 8 + ((j >> 3) & 3) * 2;
                if (hg == 0) *reinterpret_cast<uint32_t*>(g_piv + SEQ + mb * 128 + 2 * (row & 60) + 4 * (row >> 6) + (row & 3)) = __byte_perm(__float_as_uint(o[0]), __float_as_uint(o[2]), 0x7632);
            }
#pragma unroll
            for (int r = 0; r < 2; r++)
                *reinterpret_cast<uint4*>(stg + A1_SM_XA + (row + r) * 16) = make_uint4(__byte_perm(__float_as_uint(-o[2 * r]), 0, 0x3232), __float_as_uint(-o[2 * r]) >> 16, 0u, 0u);
            *reinterpret_cast<float4*>(rst + row + (row >> 6) * 8) = make_float4(o[0], o[1], o[2], o[3]);
            fence_async_smem();
            TSTAMP1T(7, 320); CSA(1);
            if (tid == 320) DBGC(44);
            __syncwarp();
            if ((tid & 31) == 0) mbar_arrive(bar_stat);
        }
        CSA(4); CSA_END;
        if (tid == 320) DBGCAL(0);
        __syncwarp();
        if (w == WOT) {
            mbar_wait(bars + 416, 0);
            mbar_wait(bar_done, 0);
            if (one) {
                bulk_load(sbase, wo + (hg * 8 + 6) * WOB, 2 * WOB, bar_wo);
                bulk_load(sbase + A1_SM_W0 + 2 * WOB, wo + (hg * 8 + 2) * WOB, WOB, bar_wo);
            }
            __syncwarp();
        }
#define FWA 11
#define FWB 10
        if (w == FWA || w == FWB) {
            const int cw = w == FWB;
            const uint32_t* fl = reinterpret_cast<const uint32_t*>(rsum + 2 * SEQ) + (((layer * 16 + mb) * 2 + cw) * 8 + (tid & 7)) * FSTR;
            const unsigned char* src = reinterpret_cast<const unsigned char*>(of) + mb * 163840 + cw * 10240 + (tid & 7) * 20480;
            const uint32_t sl = sbase + (cw ? A1_SM_A1 : A1_SM_A0);
            mbar_wait(cw ? bar_done : bar_kvf, 0);
            if (one) {
                mbar_expect_tx(bar_f2 + 64 * cw + 64, 10240);
                tma_load_3d(sl + 51200, &tmR, layer ? 0 : hg * 80, layer ? hg * 80 : mb * 64, layer ? mb * 2 + cw : cw, bar_f2 + 64 * cw + 64);
            }
            __syncwarp();
            uint32_t pend = 0xffu & ~(1u << hg), v = 0;
            const uint32_t bo = wo_off((tid & 7) + ((tid & 7) < hg)) >> 4, lt = (1u << (tid & 31)) - 1;
#pragma unroll 1
            for (int it = 0; pend && it < 2 * SPIN_MAX; it++) {
                if (v != 4 && (pend >> (tid & 31) & 1)) asm volatile(A1_FLD " %0, [%1];" : "=r"(v) : "l"(fl) : "memory");
                uint32_t fr;
                asm volatile("{\n.reg .pred p;\nmbarrier.test_wait.parity.shared::cta.b64 p, [%1], 0;\nselp.b32 %0, 1, 0, p;\n}" : "=r"(fr) : "r"(bar_e2 + 16 * cw + (tid & 1) * 8) : "memory");
                fr = __ballot_sync(~0u, fr);
                uint32_t m = __ballot_sync(~0u, v == 4 || it >= A1_FSPIN) & pend;
                const int q = 8 - __popc(pend) + __popc(m & lt);
                m &= __ballot_sync(~0u, q < ((fr & 2) ? 8 : (fr & 1) ? 7 : 5));
                pend ^= m;
                if (m >> (tid & 31) & 1) DBGC(12 + cw * 8 + (tid & 7));
                if (!m) __nanosleep(A1_FSLEEP);
                if (m >> (tid & 31) & 1) {
                    bulk_load(q == 7 && !cw ? sbase + A1_SM_W0 : sl + (q < 6 ? q : q - 6) * 10240, src, 10240, bar_f2 + 64 * cw + 8 * q);
                    asm volatile("st.shared.u32 [%0], %1;" ::"r"(que + 32 * cw + 4 * q), "r"(bo) : "memory");
                    mbar_expect_tx(bar_f2 + 64 * cw + 8 * q, 10240);
                    DBGC(44 + cw * 8 + q);
                }
                __syncwarp();
            }
        }
    } else if (tile < 128) {
        SPAN(1 + 4 * layer, 0);
        constexpr int on = 1;
        float acc[120];
        const int lane = tid & 31, warp = w & 7, g = lane >> 2, t = lane & 3;
        if (on) {
            SPAN(1 + 4 * layer, 1);
            TSTAMP1(0);
            if (threadIdx.x == 0) { GSTAMP(g_tim1, 15); }
            TSTAMP3(0);
            if (tid == 0) TSTAMP2(0);
            TSTAMP4(0);
            if (tid == 0) DBGC(60);
            if (layer == 0) a1_mainloop<0>(acc, sbase, bars, wg, tile); else a1_mainloop<1>(acc, sbase, bars, wg, tile);
            uint32_t ok;
            asm volatile("{\n.reg .pred p;\nmbarrier.test_wait.parity.shared::cta.b64 p, [%1], 0;\nselp.b32 %0, 1, 0, p;\n}" : "=r"(ok) : "r"(bar_stat) : "memory");
            if (tid == 128 && !ok) mbar_arrive(bars + 160);
            __syncwarp();
            mbar_wait(bar_stat, 0);
            wgmma_fence();
            wgmma_n240<0, 0>(acc, make_desc(sbase + A1_SM_XA + wg * 1024, 0, 128, 0), make_desc(sbase + A1_SM_XB, 0, 128, 0), 1);
            wgmma_commit();
            if (tid == 128 && ok) mbar_arrive(bars + 160);
            mbar_wait(bars + 8 * (A1_NST + 3), 1);
        }
        uint4* hp = g_halo + (((layer * 16 + mb - ((warp & 3) != 3)) * 8 + hg) * 2 + wg) * 168 + lane;
        float* hr = reinterpret_cast<float*>(hp - lane + 160) + ((warp & 3) == 3 ? g : 2 * t);
        asm volatile("" : "+l"(hp), "+l"(hr));
        const float2* rw = rst + 16 * warp + 8 * wg;
        const float rb0 = rw[g + 8].y, ra = rw[g].y * 0.22360679774997896f, rb = rb0 * 0.22360679774997896f;
        wgmma_wait<0>();
        if ((tid & 127) == 0) mbar_arrive(bar_done);
        TSTAMP1(2); CSA(1);
        TSTAMP1T(13, 224);
        if ((tid & 127) == 0) DBGC(62 - wg);
        uint32_t f[2][30];
#pragma unroll
        for (int j = 10; j < 30; j++) f[1][j] = pack2(acc[4 * j + 2], acc[4 * j + 3]);
        if ((warp & 3) == 3) {
#pragma unroll
            for (int j = 0; j < 20; j += 4) {
                const int a = j < 12 ? 10 + j : 8 + j, b = j == 8 ? 28 : a + 2;
                asm volatile("st.relaxed.gpu.global.v4.u32 [%0], {%1,%2,%3,%4};" ::"l"(hp + 8 * j), "r"(f[1][a]), "r"(f[1][a + 1]), "r"(f[1][b]), "r"(f[1][b + 1]) : "memory");
            }
            if (t == 0) asm volatile("st.relaxed.gpu.global.f32 [%0], %1;" ::"l"(hr), "f"(rb0) : "memory");
        }
        TSTAMP1T(12, 224);
        const uint32_t kvw = sbase + A1_SM_KV + (16 * warp + 8 * wg) * A1_KVP;
        const uint32_t mrow = kvw + (lane & 7) * A1_KVP + (lane >> 3) * 16;
#pragma unroll
        for (int j = 0; j < 20; j += 4) {
            const int a = j < 12 ? 10 + j : 8 + j, b = j == 8 ? 28 : a + 2;
            stsm_x4(mrow + 16 * A1_KVP + 16 * (a - 10) + (j == 8 ? (lane & 16) * 8 : 0), f[1][a], f[1][a + 1], f[1][b], f[1][b + 1]);
        }
        __syncwarp();
        if (lane == 0 && (warp & 3) != 3) mbar_arrive(bar_kv + 8 * (warp + 1));
#pragma unroll
        for (int j = 0; j < 30; j++) f[0][j] = pack2(acc[4 * j], acc[4 * j + 1]);
        stsm_x4(mrow + 8 * A1_KVP + 160, f[0][20], f[0][21], f[0][22], f[0][23]);
        stsm_x4(mrow + 8 * A1_KVP + 224, f[0][24], f[0][25], f[0][26], f[0][27]);
        asm volatile("stmatrix.sync.aligned.m8n8.x2.shared.b16 [%0], {%1,%2};" ::"r"(mrow + 8 * A1_KVP + 288), "r"(f[0][28]), "r"(f[0][29]) : "memory");
#pragma unroll
        for (int j = 0; j < 10; j++) f[1][j] = pack2(acc[4 * j + 2], acc[4 * j + 3]);
        __syncwarp();
        uint32_t vb[10][2], hv[24] = {}, *kp = hv, *vp = hv + 12;
#pragma unroll
        for (int j = 0; j < 10; j += 2) ldsm_x4_t(&vb[j][0], kvw + (8 + (lane & 15)) * A1_KVP + 160 + (lane >> 4) * 16 + 16 * j);
        const bool up0 = 2 * t > g, up1 = 2 * t + 1 > g, edge = (mb | (warp & 3)) == 0;
        float rk[4];
        auto above = [&]() {
            mbar_wait(bar_kv + 8 * warp, 0);
#pragma unroll
            for (int j = 0; j < 12; j += 4) ldsm_x4(&kp[j], mrow + 16 * j);
            rk[0] = rw[2 * t - (up0 ? 8 : 0)].y; rk[1] = rw[2 * t + 1 - (up1 ? 8 : 0)].y;
#pragma unroll
            for (int j = 0; j < 8; j += 4) ldsm_x4_t(&vp[j], mrow + 160 + 16 * j);
            asm volatile("ldmatrix.sync.aligned.m8n8.x2.trans.shared.b16 {%0,%1}, [%2];" : "=r"(vp[8]), "=r"(vp[9]) : "r"(mrow + 288) : "memory");
            __syncwarp();
            if (lane == 0) mbar_arrive(bar_kvf);
        };
        auto ask = [&]() {
            if (mb > 0) {
#pragma unroll
                for (int k = 0; k < 20; k += 4)
                    asm volatile("ld.relaxed.gpu.global.v4.u32 {%0,%1,%2,%3}, [%4];" : "=r"(hv[k]), "=r"(hv[k + 1]), "=r"(hv[k + 2]), "=r"(hv[k + 3]) : "l"(hp + 8 * k) : "memory");
                asm volatile("ld.relaxed.gpu.global.v2.u32 {%0,%1}, [%2];" : "=r"(hv[20]), "=r"(hv[21]) : "l"(hr) : "memory");
            }
        };
        auto halo = [&]() {
            if (lane == 0) mbar_arrive(bar_kvf);
            rk[0] = rw[2 * t].y; rk[1] = rw[2 * t + 1].y;
#pragma unroll 1
            for (int it = 0; it < SPIN_MAX; it++) {
                uint32_t m = max(hv[20], hv[21]);
#pragma unroll
                for (int k = 0; k < 20; k += 2) m = __vimax3_u32(m, hv[k], hv[k + 1]);
                if (!__any_sync(~0u, m == ~0u)) break;
                ask();
            }
            if (wg && lane == 0) mbar_arrive(bars + 416);
            if (up0) rk[0] = __uint_as_float(hv[20]);
            if (up1) rk[1] = __uint_as_float(hv[21]);
#pragma unroll
            for (int j = 0; j < 10; j++) asm volatile("movmatrix.sync.aligned.m8n8.trans.b16 %0, %1;" : "=r"(vp[j]) : "r"(hv[j < 8 ? 12 + j : 2 + j]));
        };
        rk[2] = rw[2 * t + (up0 ? 0 : 8)].y; rk[3] = rw[2 * t + 1 + (up1 ? 0 : 8)].y;
        uint32_t qs[4][2];
#pragma unroll
        for (int h = 0; h < 4; h++) {
            qs[h][0] = (t >> 1) == (h & 1) ? f[0][5 * (h >> 1) + 2] : 0u; qs[h][1] = (t >> 1) == (h & 1) ? f[1][5 * (h >> 1) + 2] : 0u;
            asm volatile("" : "+r"(qs[h][0]), "+r"(qs[h][1]));
        }
#pragma unroll
        for (int j = 0; j < 10; j++) asm volatile("" : "+r"(f[0][j]), "+r"(f[1][j]), "+r"(f[0][10 + j]));
        if (warp & 3) above(); else if (wg) ask(); else hv[20] = mb ? ~0u : 0u;
        TSTAMP1T(10, 64); CSA(2);
        if (warp && !wg) mbar_wait(bars + 416 + 8 * warp, 0);
        CSA(3);
        float sc[4][3][4];
#pragma unroll
        for (int h = 0; h < 4; h++) {
            const int jb = 5 * (h >> 1) + 3 * (h & 1), js = 5 * (h >> 1) + 2;
#pragma unroll
            for (int nt = 1; nt < 3; nt++) {
#pragma unroll
                for (int e = 0; e < 4; e++) sc[h][nt][e] = 0.f;
                mma_bf16(sc[h][nt], f[0][jb], f[1][jb], f[0][jb + 1], f[1][jb + 1], f[nt - 1][10 + jb], f[nt - 1][11 + jb]);
                mma_bf16_k8(sc[h][nt], qs[h][0], qs[h][1], f[nt - 1][10 + js]);
            }
        }
        if (!(warp & 3)) halo();
        TSTAMP1(8); CSA(4);
#pragma unroll
        for (int h = 0; h < 4; h++) {
            const int jb = 5 * (h >> 1) + 3 * (h & 1), js = 5 * (h >> 1) + 2;
#pragma unroll
            for (int e = 0; e < 4; e++) sc[h][0][e] = 0.f;
            mma_bf16(sc[h][0], f[0][jb], f[1][jb], f[0][jb + 1], f[1][jb + 1], kp[jb], kp[jb + 1]);
            mma_bf16_k8(sc[h][0], qs[h][0], qs[h][1], kp[js]);
        }
        TSTAMP1T(3, 64);
        float p[4][4], sum[4][2];
        uint32_t lg[4][2], mx[4];
        const float rl[4] = {rk[0] * ra, rk[1] * ra, rk[2] * rb, rk[3] * rb};
        auto max2 = [](uint32_t a, uint32_t b) { uint32_t r; asm("max.bf16x2 %0, %1, %2;" : "=r"(r) : "r"(a), "r"(b)); return r; };
#pragma unroll
        for (int h = 0; h < 4; h++) {
            lg[h][0] = pack2((up0 ? sc[h][0][0] : sc[h][1][0]) * rl[0], (up0 ? sc[h][1][2] : sc[h][2][2]) * rl[2]);
            lg[h][1] = pack2((up1 ? sc[h][0][1] : sc[h][1][1]) * rl[1], (up1 ? sc[h][1][3] : sc[h][2][3]) * rl[3]);
            if (edge) {
                if (up0) lg[h][0] = __byte_perm(lg[h][0], 0xce6eu, 0x3254);
                if (up1) lg[h][1] = __byte_perm(lg[h][1], 0xce6eu, 0x3254);
            }
            mx[h] = max2(lg[h][0], lg[h][1]);
        }
#pragma unroll
        for (int o = 1; o <= 2; o <<= 1)
#pragma unroll
            for (int h = 0; h < 4; h++) mx[h] = max2(mx[h], __shfl_xor_sync(~0u, mx[h], o));
#pragma unroll
        for (int h = 0; h < 4; h++)
#pragma unroll
            for (int r = 0; r < 2; r++) {
                const float m = __uint_as_float(r ? mx[h] & 0xffff0000u : mx[h] << 16);
#pragma unroll
                for (int e = 0; e < 2; e++)
                    asm("ex2.approx.ftz.f32 %0, %1;" : "=f"(p[h][2 * r + e]) : "f"((__uint_as_float(r ? lg[h][e] & 0xffff0000u : lg[h][e] << 16) - m) * 1.4426950408889634f));
                sum[h][r] = p[h][2 * r] + p[h][2 * r + 1];
            }
#pragma unroll
        for (int o = 1; o <= 2; o <<= 1)
#pragma unroll
            for (int h = 0; h < 4; h++)
#pragma unroll
                for (int r = 0; r < 2; r++) sum[h][r] += __shfl_xor_sync(~0u, sum[h][r], o);
        TSTAMP1T(5, 64); CSA(5);
        const uint32_t mu = (up0 ? 0xffffu : 0u) | (up1 ? 0xffff0000u : 0u);
        uint32_t ob[10][2];
#pragma unroll
        for (int P = 0; P < 2; P++) {
            float os[2][4];
#pragma unroll
            for (int e = 0; e < 2; e++) {
                const int h = 2 * P + e;
                const float i0 = rcp_apx(sum[h][0]), i1 = rcp_apx(sum[h][1]);
                const uint32_t w0 = pack2(p[h][0] * rk[0] * i0, p[h][1] * rk[1] * i0), w1 = pack2(p[h][2] * rk[2] * i1, p[h][3] * rk[3] * i1);
#pragma unroll
                for (int dt = 0; dt < 3; dt++) {
                    const int j = 5 * P + (dt < 2 ? 3 * e + dt : 2);
                    float o[4] = {0.f, 0.f, 0.f, 0.f};
                    mma_bf16(o, w0 & ~mu, w1 & mu, 0u, w1 & ~mu, vb[j][0], vb[j][1]);
                    mma_bf16_k8(o, w0 & mu, 0u, vp[j]);
                    if (dt < 2) { ob[j][0] = pack2(o[0], o[1]); ob[j][1] = pack2(o[2], o[3]); }
                    else { os[e][0] = o[0]; os[e][1] = o[1]; os[e][2] = o[2]; os[e][3] = o[3]; }
                }
            }
#pragma unroll
            for (int k = 0; k < 4; k++) os[0][k] = t < 2 ? os[0][k] : os[1][k];
            ob[5 * P + 2][0] = pack2(os[0][0], os[0][1]); ob[5 * P + 2][1] = pack2(os[0][2], os[0][3]);
        }
        const uint32_t sl = sbase + (wg ? A1_SM_A1 : A1_SM_A0);
        const uint32_t o0 = (warp & 3) * 2048 + g * 64 + ((t ^ (g >> 1)) << 4), o1 = 8192 + (warp & 3) * 512 + g * 32 + ((t ^ ((g >> 2) << 1)) << 3);
        CSA(15);
#pragma unroll
        for (int j = 0; j < 10; j++) asm volatile("" : "+r"(ob[j][0]), "+r"(ob[j][1]) :: "memory");
        if (wg == 0 && lane == 0) mbar_arrive(bar_pv);
        mbar_wait(bar_done, 0);
        if (wg == 0) mbar_wait(bar_kvf, 0);
#pragma unroll
        for (int h = 0; h < 2; h++) {
            asm volatile("st.shared.v4.u32 [%0], {%1,%2,%3,%4};" ::"r"(sl + o0 + h * 1024), "r"(ob[0][h]), "r"(ob[1][h]), "r"(ob[2][h]), "r"(ob[3][h]) : "memory");
            asm volatile("st.shared.v4.u32 [%0], {%1,%2,%3,%4};" ::"r"(sl + o0 + h * 1024 + 512), "r"(ob[4][h]), "r"(ob[5][h]), "r"(ob[6][h]), "r"(ob[7][h]) : "memory");
            asm volatile("st.shared.v2.u32 [%0], {%1,%2};" ::"r"(sl + o1 + h * 256), "r"(ob[8][h]), "r"(ob[9][h]) : "memory");
        }
        if (warp > 4 && lane == 0) mbar_arrive(bars + 384 + 8 * warp);
        fence_async_smem();
        __syncwarp();
        TSTAMP1T(4, 64); CSA(6);
        TSTAMP1(1);
        TSTAMP2(1);
        const unsigned char* ot = reinterpret_cast<const unsigned char*>(of) + mb * 163840 + wg * 10240;
        if (lane == 0) {
            asm volatile("cp.async.bulk.global.shared::cta.bulk_group [%0], [%1], 2048;" ::"l"(ot + hg * 20480 + (warp & 3) * 2048), "r"(sl + (warp & 3) * 2048) : "memory");
            asm volatile("cp.async.bulk.global.shared::cta.bulk_group [%0], [%1], 512;" ::"l"(ot + hg * 20480 + 8192 + (warp & 3) * 512), "r"(sl + 8192 + (warp & 3) * 512) : "memory");
            asm volatile("cp.async.bulk.commit_group;" ::: "memory");
            asm volatile("cp.async.bulk.wait_group 0;" ::: "memory");
            asm volatile(A1_FRED " [%0], 1;" ::"l"(reinterpret_cast<uint32_t*>(rsum + 2 * SEQ) + (((layer * 16 + mb) * 2 + wg) * 8 + hg) * FSTR) : "memory");
            DBGC(4 + warp);
        }
        TSTAMP4(11); CSA(7);
        float ac2[40];
        const uint64_t db0 = make_desc(sbase, 1024, 256, 3), db1 = make_desc(sbase + 10240, 512, 256, 3), da0 = make_desc(sl, 16, 1024, 2), da1 = make_desc(sl + 8192, 16, 256, 3);
        const uint32_t o7 = wg ? 640 : (A1_SM_W0 - A1_SM_A0) >> 4;
        const uint32_t trow = ((lane & 7) + 8 * (lane >> 4)) * 128 + (((2 * (warp & 3) + ((lane >> 3) & 1)) ^ (lane & 7)) << 4);
        uint32_t xr[10][2];
        mbar_wait(bar_f2 + 64 * wg + 64, 0);
        if (layer == 0) {
#pragma unroll
            for (int j = 0; j < 10; j += 2) ldsm_x4(&xr[j][0], sl + 51200 + (16 * (warp & 3) + (lane & 15)) * 160 + (lane >> 4) * 16 + 16 * j);
        } else {
#pragma unroll
            for (int j = 0; j < 10; j += 2) ldsm_x4_t(&xr[j][0], sl + 51200 + trow + 1024 * j);
        }
        const uint32_t ri = __shfl_sync(~0u, layer * SEQ + (wg * 2 + ((g >> 1) & 1)) * 512 + (mb * 16 + 4 * (warp & 3) + (g >> 2)) * 2 + (g & 1), lane);
        mbar_wait(bar_wo, 0);
        if (wg) asm volatile("bar.sync 2, 128;" ::: "memory"); else asm volatile("bar.sync 1, 128;" ::: "memory");
        if (wg) mbar_wait(bar_pv, 0);
        TSTAMP2(2); CSA(8);
#pragma unroll
        for (int q = 0; q < 8; q++) {
            uint32_t bo = wo_off(0) >> 4;
            if (q) {
                mbar_wait(bar_f2 + 64 * wg + 8 * q, 0);
                asm volatile("ld.shared.u32 %0, [%1];" : "=r"(bo) : "r"(que + 32 * wg + 4 * q) : "memory");
                bo = __shfl_sync(~0u, bo, 0);
                TSTAMP4(q);
                if (q % 3 == 1) CSA(9 + q / 3);
                if (q == 1 && (tid & 127) == 0) DBGC(29 + 8 * wg);
            }
            wgmma_fence();
#pragma unroll
            for (int j = 0; j < 5; j++) wgmma_n80(ac2, (j < 4 ? da0 : da1) + (q == 7 ? o7 : 0u) + (uint64_t)((q < 6 ? q * 640 : 0) + (j & 2) * 16 + (j & 1) * 2), (j < 4 ? db0 : db1) + bo + (uint64_t)((j & 2) * 160 + (j & 1) * 32), j || q);
            wgmma_commit();
            if (q == 0) {
                wgmma_wait<0>();
                if ((tid & 127) == 0) { mbar_arrive(bar_e2 + 16 * wg); mbar_arrive(bar_e2 + 8); }
            }
            if (q == 2 && wg) {
                wgmma_wait<1>();
                if (tid == 128) mbar_arrive(bar_e2 + 24);
            }
        }
        if ((tid & 127) == 0) DBGC(28 + wg * 8 + 7);
        TSTAMP2(3);
        wgmma_wait<0>();
        TSTAMP2(4); CSA(12);
        if (__any_sync(~0u, ac2[0] != ac2[0] || ac2[2] != ac2[2])) {
#pragma unroll
            for (int i = 0; i < 40; i++) ac2[i] = 0.f;
            uint32_t a[20], an[20];
            auto lda = [&](uint32_t (&r)[20], int h) {
#pragma unroll
                for (int u = 0; u < 4; u++)
                    asm volatile("ld.relaxed.gpu.global.v4.u32 {%0,%1,%2,%3}, [%4];" : "=r"(r[4 * u]), "=r"(r[4 * u + 1]), "=r"(r[4 * u + 2]), "=r"(r[4 * u + 3]) : "l"(ot + h * 20480 + o0 + u * 512) : "memory");
#pragma unroll
                for (int u = 0; u < 2; u++)
                    asm volatile("ld.relaxed.gpu.global.v2.u32 {%0,%1}, [%2];" : "=r"(r[16 + 2 * u]), "=r"(r[17 + 2 * u]) : "l"(ot + h * 20480 + o1 + u * 256) : "memory");
            };
            lda(an, 0);
#pragma unroll 5
            for (int k = lane; k < WOB / 16; k += 32)
                reinterpret_cast<uint4*>(stg + (sl - sbase))[k] = __ldcg(reinterpret_cast<const uint4*>(wo + hg * 8 * WOB) + k);
            __syncwarp();
#pragma unroll 1
            for (int h = 0; h < 8; h++) {
#pragma unroll 1
                for (int it = 0; it < SPIN_MAX; it++) {
                    uint32_t m = 0;
#pragma unroll
                    for (int k = 0; k < 20; k += 2) m = __vimax3_u32(m, an[k], an[k + 1]);
                    if (!__any_sync(~0u, m == ~0u)) break;
                    lda(an, h);
                }
#pragma unroll
                for (int k = 0; k < 20; k++) a[k] = an[k];
                lda(an, min(h + 1, 7));
                const uint32_t bp = h == hg ? sl : sbase + wo_off(h + (h < hg));
                const int r0 = 8 * ((lane & 7) >> 1) + 2 * (lane >> 3) + (lane & 1), r2 = 4 * ((lane & 7) >> 1) + 2 * ((lane >> 3) & 1) + (lane & 1);
#pragma unroll
                for (int n = 0; n < 10; n++) {
                    uint32_t b[12];
                    ldsm_x4_t(b, bp + (n >> 1) * 1024 + r0 * 32 + (((n ^ (r0 >> 2)) & 1) << 4));
                    ldsm_x4_t(b + 4, bp + 5120 + (n >> 1) * 1024 + r0 * 32 + (((n ^ (r0 >> 2)) & 1) << 4));
                    ldsm_x4_t(b + 8, bp + 10240 + (n >> 1) * 512 + r2 * 32 + (((n ^ (r2 >> 2)) & 1) << 4));
                    mma_bf16(ac2 + 4 * n, a[0], a[8], a[1], a[9], b[0], b[1]); mma_bf16(ac2 + 4 * n, a[2], a[10], a[3], a[11], b[2], b[3]);
                    mma_bf16(ac2 + 4 * n, a[4], a[12], a[5], a[13], b[4], b[5]); mma_bf16(ac2 + 4 * n, a[6], a[14], a[7], a[15], b[6], b[7]);
                    mma_bf16(ac2 + 4 * n, a[16], a[18], a[17], a[19], b[8], b[9]);
                }
            }
        }
#pragma unroll
        for (int j = 0; j < 10; j++)
#pragma unroll
            for (int hh = 0; hh < 2; hh++) {
                const uint32_t a = pack2(ac2[4 * j + 2 * hh], ac2[4 * j + 2 * hh + 1]);
                const __nv_bfloat162 r = __hadd2_rn(*reinterpret_cast<const __nv_bfloat162*>(&xr[j][hh]), *reinterpret_cast<const __nv_bfloat162*>(&a));
                xr[j][hh] = *reinterpret_cast<const uint32_t*>(&r);
            }
        const uint32_t so = sl + 30720;
#pragma unroll
        for (int j = 0; j < 10; j += 2) stsm_x4_t(so + trow + 1024 * j, xr[j][0], xr[j][1], xr[j + 1][0], xr[j + 1][1]);
        if (wg) asm volatile("bar.sync 2, 128;" ::: "memory"); else asm volatile("bar.sync 1, 128;" ::: "memory");
        TSTAMP2(5); CSA(13);
        if ((tid & 127) == 0) {
            fence_async_smem();
            asm volatile("cp.async.bulk.tensor.2d.global.shared::cta.bulk_group [%0, {%1, %2}], [%3];" ::"l"(&tmX1), "r"(mb * 128 + 64 * wg), "r"(hg * 80), "r"(so) : "memory");
            asm volatile("cp.async.bulk.commit_group;" ::: "memory");
        }
        __syncwarp();
        const float p0 = *(volatile const float*)&rw[g].x, p1 = *(volatile const float*)&rw[g + 8].x;
        float s[3][4] = {};
        const uint32_t pp[2] = {__byte_perm(__float_as_uint(p0), 0, 0x3232), __byte_perm(__float_as_uint(p1), 0, 0x3232)};
#pragma unroll
        for (int j = 0; j < 10; j += 2) {
            const uint32_t d0 = sub2(xr[j][0], pp[0]), d1 = sub2(xr[j][1], pp[1]), d2 = sub2(xr[j + 1][0], pp[0]), d3 = sub2(xr[j + 1][1], pp[1]);
            mma_bf16(s[0], xr[j][0], xr[j][1], xr[j + 1][0], xr[j + 1][1], 0x3f803f80u, 0x3f803f80u);
            mma_bf16(s[1], d0, d1, d2, d3, d0, d2);
            mma_bf16(s[2], d0, d1, d2, d3, d1, d3);
        }
        if (t == (g >> 1)) {
            float2* rp = rsum + ri;
            constexpr float idm = 1.0f / DM;
            asm volatile("red.relaxed.gpu.global.add.v2.f32 [%0], {%1, %2};" ::"l"(rp), "f"(fmaf(-80.f, p0, s[0][0]) * idm), "f"(((g & 1) ? s[1][1] : s[1][0]) * idm) : "memory");
            asm volatile("red.relaxed.gpu.global.add.v2.f32 [%0], {%1, %2};" ::"l"(rp + 4), "f"(fmaf(-80.f, p1, s[0][2]) * idm), "f"(((g & 1) ? s[2][3] : s[2][2]) * idm) : "memory");
        }
        asm volatile("cp.async.bulk.wait_group.read 0;" ::: "memory");
        TSTAMP2(6); CSA(14); CSA_END;
        if (tid == 0) DBGC(63);
        if (tid == 128) DBGC(28);
        if (tid == 0) DBGCAL(2);
        GSTAMP(g_tim1, 14);
        SPAN(1 + 4 * layer, 3);
    }
#undef layer
}

static int h_nsm;
static void* h_sym[11];
static TileTab h_tab[2];
static CUtensorMap h_tmX0, h_tmX1, h_tmR0, h_tmR1, h_tmX1st, h_tmOut;
static KgMaps h_tmW;
typedef CUresult (*PFN_encodeTiled)(CUtensorMap*, CUtensorMapDataType, cuuint32_t, void*, const cuuint64_t*, const cuuint64_t*,
                                    const cuuint32_t*, const cuuint32_t*, CUtensorMapInterleave, CUtensorMapSwizzle,
                                    CUtensorMapL2promotion, CUtensorMapFloatOOBfill);
static void make_tmap(CUtensorMap* tm, const void* ptr, uint64_t cols, uint64_t rows, uint32_t bc, uint32_t br, CUtensorMapSwizzle sw, uint64_t pitch = 0, uint64_t hi = 0, uint32_t bh = 2) {
    static PFN_encodeTiled fn = nullptr;
    if (!fn) {
        void* p = nullptr; cudaDriverEntryPointQueryResult qr;
        cudaGetDriverEntryPoint("cuTensorMapEncodeTiled", &p, cudaEnableDefault, &qr);
        fn = (PFN_encodeTiled)p;
    }
    if (br == 0) {
        cuuint64_t dims[5] = {16, 2, rows / 8, 4, cols / 16}; cuuint64_t strides[4] = {cols * 2, cols * 16, cols * 4, 32};
        cuuint32_t box[5] = {16, 2, bc, 4, 5}; cuuint32_t es[5] = {1, 1, 1, 1, 1};
        fn(tm, CU_TENSOR_MAP_DATA_TYPE_BFLOAT16, 5, const_cast<void*>(ptr), dims, strides, box, es, CU_TENSOR_MAP_INTERLEAVE_NONE, sw,
           CU_TENSOR_MAP_L2_PROMOTION_L2_128B, CU_TENSOR_MAP_FLOAT_OOB_FILL_NONE);
        return;
    }
    if (hi == 16) {
        cuuint64_t dims[4] = {16, 32, 120, 20}; cuuint64_t strides[3] = {3840, 32, 32 * 3840};
        cuuint32_t box[4] = {16, 32, 5, 2}; cuuint32_t es[4] = {1, 1, 1, 1};
        fn(tm, CU_TENSOR_MAP_DATA_TYPE_BFLOAT16, 4, const_cast<void*>(ptr), dims, strides, box, es, CU_TENSOR_MAP_INTERLEAVE_NONE, sw,
           CU_TENSOR_MAP_L2_PROMOTION_L2_128B, CU_TENSOR_MAP_FLOAT_OOB_FILL_NONE);
        return;
    }
    if (bh == 0) {
        cuuint64_t dims[5] = {64, 64, 2, 16, 10}; cuuint64_t strides[4] = {pitch * 2, hi * 2, cols * 2, rows * 2};
        cuuint32_t box[5] = {64, 64, 2, 1, 1}; cuuint32_t es[5] = {1, 1, 1, 1, 1};
        fn(tm, CU_TENSOR_MAP_DATA_TYPE_BFLOAT16, 5, const_cast<void*>(ptr), dims, strides, box, es, CU_TENSOR_MAP_INTERLEAVE_NONE, sw,
           CU_TENSOR_MAP_L2_PROMOTION_L2_128B, CU_TENSOR_MAP_FLOAT_OOB_FILL_NONE);
        return;
    }
    if (hi) {
        cuuint64_t dims[3] = {cols, rows, hi == 64 ? 32u : 2u}; cuuint64_t strides[2] = {pitch * 2, hi * 2};
        cuuint32_t box[3] = {bc, br, bh}; cuuint32_t es[3] = {1, 1, 1};
        fn(tm, CU_TENSOR_MAP_DATA_TYPE_BFLOAT16, 3, const_cast<void*>(ptr), dims, strides, box, es, CU_TENSOR_MAP_INTERLEAVE_NONE, sw,
           CU_TENSOR_MAP_L2_PROMOTION_L2_128B, CU_TENSOR_MAP_FLOAT_OOB_FILL_NONE);
        return;
    }
    cuuint64_t dims[2] = {cols, rows}; cuuint64_t strides[1] = {(pitch ? pitch : cols) * 2};
    cuuint32_t box[2] = {bc, br}; cuuint32_t es[2] = {1, 1};
    fn(tm, CU_TENSOR_MAP_DATA_TYPE_BFLOAT16, 2, const_cast<void*>(ptr), dims, strides, box, es, CU_TENSOR_MAP_INTERLEAVE_NONE, sw,
       CU_TENSOR_MAP_L2_PROMOTION_L2_128B, CU_TENSOR_MAP_FLOAT_OOB_FILL_NONE);
}
template <typename... Args>
static void launch_pdl(void (*kern)(Args...), int grid, int block, int smem, Args... args) {
    cudaLaunchConfig_t cfg = {};
    cfg.gridDim = dim3(grid); cfg.blockDim = dim3(block); cfg.dynamicSmemBytes = smem; cfg.stream = cudaStreamPerThread;
    cudaLaunchAttribute at[1];
    at[0].id = cudaLaunchAttributeProgrammaticStreamSerialization; at[0].val.programmaticStreamSerializationAllowed = 1;
    cfg.attrs = at; cfg.numAttrs = 1;
    cudaLaunchKernelEx(&cfg, kern, args...);
}
static void launch_stage(int k, void* const* d_in, void* d_out) {
    const Par par = {k > 1 ? nullptr : (const bf16*)d_in[4], (const bf16*)d_in[5], (const bf16*)d_in[6], (const bf16*)d_in[7], (const bf16*)d_in[8], (const bf16*)d_in[9], k > 1, 0, (const bf16*)d_in[0],
                     (uint4*)h_sym[4], (uint4*)h_sym[2], (uint4*)h_sym[6], (uint4*)h_sym[3], (uint4*)h_sym[0], (float*)h_sym[5], (uint4*)h_sym[1], (const bf16*)d_in[1], (const bf16*)d_in[2]};
    auto a1 = h_nsm == 132 ? a1_kernel<true> : a1_kernel<false>;
    switch (k) {
        case 1: a1<<<h_nsm, A1_THREADS, A1_SMEM, cudaStreamPerThread>>>(par, h_tmX0, h_tmR0, h_tmX1st, h_tmW, h_tab[0]); break;
        case 3: launch_pdl(conv_kernel, DM / CV_CPB, CV_THREADS, CV_SMEM, 0, (const uint4*)h_sym[7], (const float4*)h_sym[4], (const bf16*)h_sym[8], (bf16*)h_sym[9], (const uint4*)h_sym[0], h_tmOut); break;
        case 5: launch_pdl(a1, h_nsm, A1_THREADS, A1_SMEM, par, h_tmX1, h_tmR1, h_tmX1st, h_tmW, h_tab[1]); break;
        case 7: launch_pdl(conv_kernel, DM / CV_CPB, CV_THREADS, CV_SMEM, 1, (const uint4*)h_sym[7] + SEQ / 8, (const float4*)h_sym[4] + SEQ / 2, (const bf16*)h_sym[8], (bf16*)h_sym[10], (const uint4*)h_sym[0], h_tmOut); break;
        default: break;
    }
}
static int n_stage_kernels() { return 9; }
static const char* stage_name(int k) { const char* n[] = {"kgen", "a1", "a2", "conv", "tr", "a1", "a2", "conv", "tr"}; return n[k]; }

extern "C" void kernel_launch(void* const* d_in, const int* in_sizes, int n_in, void* d_out, int out_size) {
    (void)in_sizes; (void)n_in; (void)out_size;
    static const void *p_in = nullptr, *p_w1 = nullptr, *p_w2 = nullptr, *p_out = nullptr;
    if (p_in != d_in[0] || p_w1 != d_in[1] || p_w2 != d_in[2] || p_out != d_out) {
        cudaFuncSetAttribute(conv_kernel, cudaFuncAttributeMaxDynamicSharedMemorySize, CV_SMEM);
        cudaFuncSetAttribute(a1_kernel<true>, cudaFuncAttributeMaxDynamicSharedMemorySize, A1_SMEM);
        cudaFuncSetAttribute(a1_kernel<false>, cudaFuncAttributeMaxDynamicSharedMemorySize, A1_SMEM);
        int dev; cudaGetDevice(&dev); cudaDeviceGetAttribute(&h_nsm, cudaDevAttrMultiProcessorCount, dev);
        if (h_nsm != 132) h_nsm = 128;
        cudaGetSymbolAddress(&h_sym[0], g_tap); cudaGetSymbolAddress(&h_sym[1], g_wq); cudaGetSymbolAddress(&h_sym[2], g_wo);
        cudaGetSymbolAddress(&h_sym[3], g_halo); cudaGetSymbolAddress(&h_sym[4], g_sum); cudaGetSymbolAddress(&h_sym[5], g_csp); cudaGetSymbolAddress(&h_sym[6], g_of);
        cudaGetSymbolAddress(&h_sym[7], g_piv); cudaGetSymbolAddress(&h_sym[8], g_x1T); cudaGetSymbolAddress(&h_sym[9], g_xcT); cudaGetSymbolAddress(&h_sym[10], g_yT);
        for (int i = 0; i < 264; i++) {
            const int s = i % 132, h = (s - 64) >> 1;
            const int t = h_nsm != 132 ? s : s < 64 ? ((s >> 1) & 7) * 16 + (s >> 4) * 2 + (s & 1) : s < 120 ? (1 + h % 7) * 16 + 8 + (h / 7) * 2 + (s & 1) : s < 124 ? 128 : s - 116;
            const int hg = (4 * (t >> 6) + (t & 3)) & 7;
            const uint64_t wp = (uint64_t)h_sym[1] + hg * 10 * WQ_STAGE;
            h_tab[i / 132].e[s] = make_uint4((uint32_t)wp, (uint32_t)(wp >> 32), ((t >> 2) & 15) | (i / 132) << 4 | hg << 8 | 5 * (hg >> 2) << 16 | (uint32_t)t << 24, 0);
        }
        void *px1, *px2;
        cudaGetSymbolAddress(&px1, g_x1T); cudaGetSymbolAddress(&px2, g_xcT);
        make_tmap(&h_tmX0, d_in[0], 128 * 640, 64, 64, 64, CU_TENSOR_MAP_SWIZZLE_128B, 1280, 640, 0);
        make_tmap(&h_tmX1, px2, 128, 64 * XCP, 64, 64, CU_TENSOR_MAP_SWIZZLE_128B, XCP, 64, 0);
        make_tmap(&h_tmR0, d_in[0], 640, 1024, 80, 64, CU_TENSOR_MAP_SWIZZLE_NONE, 1280, 640, 1);
        make_tmap(&h_tmR1, px2, 64, 640, 64, 80, CU_TENSOR_MAP_SWIZZLE_128B, XCP, 64, 1);
        make_tmap(&h_tmX1st, px1, 2048, 640, 64, 80, CU_TENSOR_MAP_SWIZZLE_128B, XCP);
        make_tmap(&h_tmW.q, d_in[1], 16, 640, 16, 32, CU_TENSOR_MAP_SWIZZLE_32B, 1920, 16, 5);
        make_tmap(&h_tmW.o, d_in[2], 640, 640, 4, 0, CU_TENSOR_MAP_SWIZZLE_32B);
        make_tmap(&h_tmW.t, d_in[2], 640, 640, 2, 0, CU_TENSOR_MAP_SWIZZLE_32B);
        make_tmap(&h_tmOut, d_out, 640, 1024, 80, 8, CU_TENSOR_MAP_SWIZZLE_NONE, 1280, 640, 1);
        p_in = d_in[0]; p_w1 = d_in[1]; p_w2 = d_in[2]; p_out = d_out;
    }
    for (int k = 0; k < n_stage_kernels(); k++) launch_stage(k, d_in, d_out);
}
```

```cpp
#include <cuda_runtime.h>
#include <cuda_bf16.h>
#include <cuda_fp16.h>
#include <stdint.h>
#include <cuda.h>

typedef __nv_bfloat16 bf16;

constexpr int SEQ = 2048;
constexpr int DM = 640;
constexpr int NMODE = 192;

__device__ __forceinline__ float bf2f(bf16 v) { return __bfloat162float(v); }
__device__ __forceinline__ float rbf(float v) {
    uint32_t r;
    asm("cvt.rn.bf16x2.f32 %0, %1, %2;" : "=r"(r) : "f"(v), "f"(0.f));
    return __uint_as_float(r);
}
__device__ __forceinline__ uint32_t pack2(float lo, float hi) {
    __nv_bfloat162 t = __floats2bfloat162_rn(lo, hi);
    return *reinterpret_cast<uint32_t*>(&t);
}
__device__ __forceinline__ void pdl_sync() {
    asm volatile("griddepcontrol.wait;" ::: "memory");
    asm volatile("griddepcontrol.launch_dependents;" ::: "memory");
}
__device__ __forceinline__ void pause(uint32_t n) { uint32_t c0, c1; asm volatile("mov.u32 %0, %clock;" : "=r"(c0) :: "memory"); do asm volatile("mov.u32 %0, %clock;" : "=r"(c1) :: "memory"); while (c1 - c0 < n); }
__device__ __forceinline__ float sqrt_apx(float v) { float r; asm("sqrt.approx.ftz.f32 %0, %1;" : "=f"(r) : "f"(v)); return r; }
__device__ __forceinline__ float rcp_apx(float v) { float r; asm("rcp.approx.ftz.f32 %0, %1;" : "=f"(r) : "f"(v)); return r; }
__device__ __forceinline__ uint32_t smem_u32(const void* p) { return (uint32_t)__cvta_generic_to_shared(p); }

constexpr int TAPB = 2944, TAPE = 928;
__device__ __align__(128) uint4 g_tap[DM * TAPB / 16];
#define XPAD 64
constexpr int XCP = SEQ + XPAD;
__device__ __align__(128) bf16 g_x1T[DM * XCP];
__device__ __align__(128) bf16 g_xcT[DM * XCP];
__device__ __align__(128) uint4 g_of[128 * 1280];
constexpr int WQ_STAGE = 240 * 128, WOB = 80 * 160;
__device__ __align__(128) uint4 g_wq[8 * 10 * WQ_STAGE / 16];
__device__ __align__(128) uint4 g_wo[64 * WOB / 16];
__device__ __align__(128) uint4 g_xb[128 * 240];
__device__ __align__(16) float g_csp[10 * 1920];
#define FSTR 32
__device__ __align__(128) float2 g_sum[2 * SEQ + 256 * FSTR];
__device__ __align__(16) bf16 g_piv[2 * SEQ];
__device__ __align__(128) bf16 g_yT[DM * XCP];
__device__ uint32_t g_epoch;
__device__ __align__(16) unsigned long long g_rstat[SEQ];
__device__ __align__(128) uint4 g_halo[640 * 148];
__device__ __forceinline__ unsigned long long tagw(uint32_t payload, uint32_t tag) { return ((unsigned long long)tag << 32) | payload; }
__device__ __forceinline__ ulonglong2 ld_tag2(const ulonglong2* p) {
    ulonglong2 v;
    asm volatile("ld.relaxed.gpu.global.v2.u64 {%0, %1}, [%2];" : "=l"(v.x), "=l"(v.y) : "l"(p) : "memory");
    return v;
}
__device__ __forceinline__ bool tag_ok(ulonglong2 v, uint32_t tag) { return (uint32_t)(v.x >> 32) == tag && (uint32_t)(v.y >> 32) == tag; }
__device__ __forceinline__ uint32_t ld_epoch() { uint32_t v; asm volatile("ld.relaxed.gpu.global.u32 %0, [%1];" : "=r"(v) : "l"(&g_epoch) : "memory"); return v + 1; }
constexpr int SPIN_MAX = 1 << 20;
__device__ __align__(128) uint32_t g_started[11 * 32];
__device__ __forceinline__ void sm_started(int slot) { asm volatile("red.relaxed.gpu.global.add.u32 [%0], 1;" ::"l"(g_started + slot) : "memory"); }
__device__ __forceinline__ void publish(int slot) {
    asm volatile("fence.proxy.async.global;" ::: "memory");
    asm volatile("red.release.gpu.global.add.u32 [%0], 1;" ::"l"(g_started + slot) : "memory");
}
__device__ __forceinline__ void await_all(int slot, uint32_t want) {
#pragma unroll 1
    for (int it = 0; it < SPIN_MAX; it++) {
        uint32_t v;
        asm volatile("ld.acquire.gpu.global.u32 %0, [%1];" : "=r"(v) : "l"(g_started + slot) : "memory");
        if (__all_sync(~0u, (int)(v - want) >= 0)) break;
        __nanosleep(50);
    }
    asm volatile("fence.proxy.async.global;" ::: "memory");
}
__device__ __noinline__ void sm_idle(int slot) {
    if (threadIdx.x != 288) return;
    asm volatile("fence.acq_rel.gpu;" ::: "memory");
    asm volatile("fence.proxy.async.global;" ::: "memory");
    sm_started(slot);
    const uint32_t want = ld_epoch() * gridDim.x;
    pdl_sync();
#pragma unroll 1
    for (int it = 0; it < SPIN_MAX; it++) {
        uint32_t v;
        asm volatile("ld.relaxed.gpu.global.u32 %0, [%1];" : "=r"(v) : "l"(g_started + slot) : "memory");
        if ((int)(v - want) >= 0) break;
        __nanosleep(100);
    }
}
struct TileTab { uint4 e[132]; };
__device__ __forceinline__ bool elect() {
    uint32_t p;
    asm volatile("{\n.reg .pred p;\nelect.sync _|p, 0xffffffff;\nselp.b32 %0, 1, 0, p;\n}" : "=r"(p));
    return p;
}
#define DBG_SYMS
#define TSTAMP(i)
#define TSTAMP1(i)
#define TSTAMP1T(i, t)
#define TSTAMP1X(i, t)
#define SPAN(k, i)
#define GSTAMP(arr, i)
#define TSTAMP2(i)
#define TSTAMP3(i)
#define TSTAMP4(i)
#define TSTAMPK(i, t)
#define TSTAMPC(i)
#define DBGC(i)
#define DBGV(i, v)
#define DBGCAL(i)

#define CSK(i)
#define CSK_END
#define CSA(i)
#define CSA_END
#define CST(i)
#define CST_END
#define CST_EXTRA 0
__device__ __forceinline__ void mma_bf16(float* d, uint32_t a0, uint32_t a1, uint32_t a2, uint32_t a3, uint32_t b0, uint32_t b1) {
    asm volatile("mma.sync.aligned.m16n8k16.row.col.f32.bf16.bf16.f32 {%0,%1,%2,%3}, {%4,%5,%6,%7}, {%8,%9}, {%0,%1,%2,%3};"
                 : "+f"(d[0]), "+f"(d[1]), "+f"(d[2]), "+f"(d[3]) : "r"(a0), "r"(a1), "r"(a2), "r"(a3), "r"(b0), "r"(b1));
}
__device__ __forceinline__ void mma_bf16_k8(float* d, uint32_t a0, uint32_t a1, uint32_t b0) {
    asm volatile("mma.sync.aligned.m16n8k8.row.col.f32.bf16.bf16.f32 {%0,%1,%2,%3}, {%4,%5}, {%6}, {%0,%1,%2,%3};"
                 : "+f"(d[0]), "+f"(d[1]), "+f"(d[2]), "+f"(d[3]) : "r"(a0), "r"(a1), "r"(b0));
}
__device__ __forceinline__ void ldsm_x4(uint32_t* r, uint32_t addr) {
    asm volatile("ldmatrix.sync.aligned.m8n8.x4.shared.b16 {%0,%1,%2,%3}, [%4];"
                 : "=r"(r[0]), "=r"(r[1]), "=r"(r[2]), "=r"(r[3]) : "r"(addr));
}

__device__ __forceinline__ void ldsm_x4_t(uint32_t* r, uint32_t addr) {
    asm volatile("ldmatrix.sync.aligned.m8n8.x4.trans.shared.b16 {%0,%1,%2,%3}, [%4];"
                 : "=r"(r[0]), "=r"(r[1]), "=r"(r[2]), "=r"(r[3]) : "r"(addr));
}
__device__ __forceinline__ void mbar_init(uint32_t bar, int count) { asm volatile("mbarrier.init.shared::cta.b64 [%0], %1;" ::"r"(bar), "r"(count)); }
__device__ __forceinline__ void mbar_arrive(uint32_t bar) { asm volatile("mbarrier.arrive.shared::cta.b64 _, [%0];" ::"r"(bar) : "memory"); }
__device__ __forceinline__ void mbar_wait(uint32_t bar, uint32_t parity) {
    asm volatile("{\n.reg .pred p;\nWAIT_LOOP:\n"
                 "mbarrier.try_wait.parity.shared::cta.b64 p, [%0], %1;\n"
                 "@p bra.uni WAIT_DONE;\nbra.uni WAIT_LOOP;\nWAIT_DONE:\n}" ::"r"(bar), "r"(parity) : "memory");
}

__device__ __forceinline__ void mbar_expect_tx(uint32_t bar, uint32_t bytes) {
    asm volatile("mbarrier.arrive.expect_tx.shared::cta.b64 _, [%0], %1;" ::"r"(bar), "r"(bytes) : "memory");
}
__device__ __forceinline__ void tma_load_2d(uint32_t dst, const void* tmap, int c0, int c1, uint32_t bar) {
    asm volatile("cp.async.bulk.tensor.2d.shared::cluster.global.mbarrier::complete_tx::bytes [%0], [%1, {%3, %4}], [%2];"
                 ::"r"(dst), "l"(tmap), "r"(bar), "r"(c0), "r"(c1) : "memory");
}
__device__ __forceinline__ void tma_load_3d(uint32_t dst, const void* tmap, int c0, int c1, int c2, uint32_t bar) {
    asm volatile("cp.async.bulk.tensor.3d.shared::cluster.global.mbarrier::complete_tx::bytes [%0], [%1, {%3, %4, %5}], [%2];"
                 ::"r"(dst), "l"(tmap), "r"(bar), "r"(c0), "r"(c1), "r"(c2) : "memory");
}
__device__ __forceinline__ void fence_async_smem() { asm volatile("fence.proxy.async.shared::cta;" ::: "memory"); }
__device__ __forceinline__ void bulk_load(uint32_t dst, const void* src, uint32_t bytes, uint32_t bar) {
    asm volatile("cp.async.bulk.shared::cluster.global.mbarrier::complete_tx::bytes [%0], [%1], %2, [%3];"
                 ::"r"(dst), "l"(src), "r"(bytes), "r"(bar) : "memory");
}
__device__ __forceinline__ void stsm_x4(uint32_t addr, uint32_t r0, uint32_t r1, uint32_t r2, uint32_t r3) {
    asm volatile("stmatrix.sync.aligned.m8n8.x4.shared.b16 [%0], {%1,%2,%3,%4};" ::"r"(addr), "r"(r0), "r"(r1), "r"(r2), "r"(r3) : "memory");
}
__device__ __forceinline__ void stsm_x4_t(uint32_t addr, uint32_t r0, uint32_t r1, uint32_t r2, uint32_t r3) {
    asm volatile("stmatrix.sync.aligned.m8n8.x4.trans.shared.b16 [%0], {%1,%2,%3,%4};" ::"r"(addr), "r"(r0), "r"(r1), "r"(r2), "r"(r3) : "memory");
}
__device__ __forceinline__ void prefetch_tmap(const void* tmap) { asm volatile("prefetch.tensormap [%0];" ::"l"(tmap) : "memory"); }

__device__ __forceinline__ float2 cexp_at(float wr2, float wi, float p) {
    float er;
    asm("ex2.approx.ftz.f32 %0, %1;" : "=f"(er) : "f"(wr2 * p));
    float th = wi * p;
    const float k = rintf(th * 0.15915494309189535f);
    th = fmaf(k, -6.2831854820251465f, th);
    th = fmaf(k, 1.7484555314695172e-7f, th);
    return make_float2(er * __cosf(th), er * __sinf(th));
}
__device__ __forceinline__ float2 cmul(float2 a, float2 b) {
    return make_float2(fmaf(a.x, b.x, -a.y * b.y), fmaf(a.x, b.y, a.y * b.x));
}
__device__ __forceinline__ float2 csqr(float2 a) { return make_float2(fmaf(a.x, a.x, -a.y * a.y), (a.x + a.x) * a.y); }
__device__ __forceinline__ uint32_t packh(float2 v) {
    uint32_t r;
    asm("cvt.rn.f16x2.f32 %0, %1, %2;" : "=r"(r) : "f"(v.y), "f"(v.x));
    return r;
}
__device__ __forceinline__ uint2 packr(float2 v) { return make_uint2(packh(v), packh(make_float2(-v.y, v.x))); }
__device__ __forceinline__ uint32_t hcmul(uint32_t a, uint2 b) {
    const __half2 x = *reinterpret_cast<const __half2*>(&a);
    const __half2 r = __hfma2(__high2half2(x), *reinterpret_cast<const __half2*>(&b.y), __hmul2(__low2half2(x), *reinterpret_cast<const __half2*>(&b.x)));
    return *reinterpret_cast<const uint32_t*>(&r);
}

struct Par { const bf16 *logA, *Aim, *Cre, *Cim, *logdt, *dsk; int layer, pad; const bf16* x; uint4 *sum, *wop, *of, *halo, *tap; float* csp; uint4* wq; const bf16 *wqkv, *wo; };
struct KgMaps { CUtensorMap q, o, t; };

__device__ __forceinline__ void bulk_prefetch(const void* p, uint32_t bytes) { asm volatile("cp.async.bulk.prefetch.L2.global [%0], %1;" ::"l"(p), "r"(bytes) : "memory"); }
__device__ __forceinline__ void bulk_store(void* dst, uint32_t src, uint32_t bytes) { asm volatile("cp.async.bulk.global.shared::cta.bulk_group [%0], [%1], %2;" ::"l"(dst), "r"(src), "r"(bytes) : "memory"); }
__device__ __forceinline__ void kgen_first(const Par& in, const KgMaps& tm, const uint32_t b0, const uint32_t wbar, const bool one) {
    const uint32_t blk = blockIdx.x, sec = (blk >= 40) + (blk >= 80), it = (blk >> 3) - 5 * sec, up = (blk >> 2) & 1, hi = blk >> 6;
    auto fetch = [&](int h) {
        if (blk < 120) asm volatile("cp.async.bulk.tensor.4d.shared::cluster.global.mbarrier::complete_tx::bytes [%0], [%1, {%3, %3, %4, %5}], [%2];"
                                    ::"r"(b0 + 10240 * h), "l"(&tm.q), "r"(wbar + 8 * h), "r"(0), "r"(sec * 40 + (blk & 7) * 5), "r"(2 * it + 10 * (up ^ h)) : "memory");
    };
    auto fetch_o = [&](int i) {
        asm volatile("cp.async.bulk.tensor.5d.shared::cluster.global.mbarrier::complete_tx::bytes [%0], [%1, {%3, %3, %4, %3, %5}], [%2];"
                     ::"r"(b0 + 20480 + i * 5120), "l"(&tm.o + i), "r"(wbar + 16), "r"(0), "r"((blk & 7) * 10 + (hi + i) * 4), "r"(((blk >> 3) & 7) * 5) : "memory");
    };
    if (one) {
#pragma unroll
        for (int i = 0; i < 3; i++) mbar_init(wbar + 8 * i, 1);
        asm volatile("fence.mbarrier_init.release.cluster;" ::: "memory");
        fetch(0);
    }
    __syncwarp();
    if (blk >> 20) __trap();
    if (one) {
        bulk_prefetch(in.wqkv + blk * 9600, 19200);
        fetch(1);
        bulk_prefetch(in.wo + blk * 3200, 6400);
        fetch_o(0);
        if (hi) fetch_o(1);
        mbar_expect_tx(wbar, 10240); mbar_expect_tx(wbar + 8, 10240); mbar_expect_tx(wbar + 16, 5120 + hi * 2560);
        bulk_prefetch(in.x + blk * 10240, 20480);
    }
}
__device__ __forceinline__ void kgen_side(const Par& in, const uint32_t b0, const uint32_t wbar) {
    const uint32_t blk = blockIdx.x, sec = (blk >= 40) + (blk >= 80), it = (blk >> 3) - 5 * sec, cg = (blk >> 3) & 7, hb = blk & 7;
    unsigned char* dst = reinterpret_cast<unsigned char*>(in.wq) + (hb * 10 + it) * WQ_STAGE + sec * 5120;
    if (blk < 120) {
        mbar_wait(wbar, 0);
        CSK(2);
        bulk_store(dst, b0, 5120); bulk_store(dst + 15360, b0 + 5120, 5120);
        mbar_wait(wbar + 8, 0);
        CSK(3);
        bulk_store(dst + 5 * WQ_STAGE, b0 + 10240, 5120); bulk_store(dst + 5 * WQ_STAGE + 15360, b0 + 15360, 5120);
        asm volatile("cp.async.bulk.commit_group;" ::: "memory");
        asm volatile("cp.async.bulk.wait_group 0;" ::: "memory");
        CSK(4);
        publish(96 + 32 * hb);
        CSK(5);
    }
    if (blk < 128) {
        mbar_wait(wbar + 16, 0);
        bulk_store(reinterpret_cast<unsigned char*>(in.wop) + (cg * 8 + (hb == cg ? 0 : hb + (hb < cg))) * WOB + (blk >> 6) * 5120, b0 + 20480, blk < 64 ? 5120 : 7680);
        asm volatile("cp.async.bulk.commit_group;" ::: "memory");
    }
}
__device__ __forceinline__ void kgen_sums(const Par& in, const uint32_t b0, const int h) {
    const int lane = threadIdx.x & 31, blk = blockIdx.x;
    if (blk < 120) {
        float cs[5][4] = {};
#pragma unroll
        for (int a = 0; a < 4; a++)
#pragma unroll
            for (int j = 0; j < 5; j++) {
                uint32_t w[4];
                ldsm_x4_t(w, b0 + h * 10240 + j * 1024 + ((lane >> 4) * 8 + (lane & 7)) * 32 + ((((lane >> 3) ^ (lane >> 2)) & 1) << 4) + (a >> 1) * 5120 + (a & 1) * 512);
                mma_bf16(cs[j], w[0], w[1], w[2], w[3], 0x3f803f80u, 0x3f803f80u);
            }
#pragma unroll
        for (int j = 0; j < 5; j++)
            if ((lane & 3) < 2) in.csp[(blk + 120 * h) * 80 + j * 16 + (lane >> 2) + 8 * (lane & 3)] = (lane & 3) ? cs[j][2] : cs[j][0];
    }
}
struct KgPar { uint32_t pw[4], ph[4], pdt, pdsk; };
__device__ __forceinline__ void kgen_load(const Par& in, const bf16* logA, const int w11, KgPar& k) {
    const uint32_t o = blockIdx.x * 480 + min(w11 * 48, w11 * 32 + 128), ow = o + (threadIdx.x & 31), oh = o + ow + (w11 < 8 ? 64 : 0);
    k.pdt = reinterpret_cast<const unsigned short*>(in.logdt)[ow / 96];
    k.pdsk = reinterpret_cast<const unsigned short*>(in.dsk)[ow / 96];
#pragma unroll
    for (int i = 0; i < 4; i++) {
        const bf16* p = i == 0 ? logA : i == 1 ? in.Aim : i == 2 ? in.Cre : in.Cim;
        k.pw[i] = reinterpret_cast<const uint32_t*>(p)[ow]; k.ph[i] = reinterpret_cast<const unsigned short*>(p)[oh];
    }
}
__device__ __forceinline__ void kgen_tables(const Par& in, uint4* tabs, const int w11, const KgPar& kp) {
    const int lane = threadIdx.x & 31, grp = min(w11 >> 1, 4), warp = w11 - 2 * grp;
    const int blk = blockIdx.x, d = blk * 5 + grp, tid = warp * 32 + lane;
    uint4* tab = tabs + grp * (2 * 256);
    const uint32_t *pw = kp.pw, *ph = kp.ph;
#pragma unroll
    for (int i = 0; i < 3; i++)
        if (i < 2 || w11 * 32 + lane < 36) asm volatile("st.global.v4.u32 [%0], {%1,%1,%1,%1};" ::"l"(in.halo + blk * 740 + w11 * 32 + lane + 352 * i), "r"(~0u));
    __syncwarp();
    if (w11 == 10) {
        if (lane < 16) in.sum[blk * 16 + lane] = make_uint4(0, 0, 0, 0);
        else if (lane < 20) reinterpret_cast<uint32_t*>(in.sum + 2048)[(blk * 4 + lane - 16) * FSTR] = 0;
    } else if (w11 > 1) asm volatile("bar.arrive 9, 352;" ::: "memory");
#pragma unroll
    for (int i = 0; i < 6; i++) tabs[w11 * 256 + 32 * i + lane] = make_uint4(0, 0, 0, 0);
    __syncwarp();
    CSK(1);
    const uint32_t tw = smem_u32(tabs) + w11 * 4096;
    const int g = lane >> 2, t = lane & 3;
    const int mt = lane >> 3, r = lane & 7;
    const uint32_t st1 = tw + mt * 1024 + r * 16, st2 = tw + (mt & 1) * 1024 + (mt >> 1) * 128 + ((r ^ (mt >> 1)) << 4), st3 = tw + 2048 + mt * 128 + ((r ^ mt) << 4);
    const uint32_t lda = tw + (mt & 1) * 1024 + r * 128 + (((mt >> 1) ^ r) << 4), ldb = tw + (mt >> 1) * 1024 + r * 128 + (((mt & 1) ^ r) << 4), ldc = tw + 2048 + r * 128 + ((mt ^ r) << 4);
    auto ldsm = [](uint32_t* v, uint32_t a) {
        asm volatile("ldmatrix.sync.aligned.m8n8.x4.shared.b16 {%0,%1,%2,%3}, [%4];" : "=r"(v[0]), "=r"(v[1]), "=r"(v[2]), "=r"(v[3]) : "r"(a) : "memory");
    };
    auto mma = [](float* c, const uint32_t* a, const uint32_t* b) {
        asm("mma.sync.aligned.m16n8k16.row.col.f32.f16.f16.f32 {%0,%1,%2,%3}, {%4,%5,%6,%7}, {%8,%9}, {%0,%1,%2,%3};"
            : "+f"(c[0]), "+f"(c[1]), "+f"(c[2]), "+f"(c[3]) : "r"(a[0]), "r"(a[1]), "r"(a[2]), "r"(a[3]), "r"(b[0]), "r"(b[1]));
    };
    asm volatile("st.shared.u32 [%0], %1;" ::"r"(tw + 3072), "r"(st1 ^ st2 ^ st3 ^ lda ^ ldb ^ ldc) : "memory");
    if (in.pad) __trap();
    const float dt = rbf(expf(__uint_as_float(kp.pdt << 16)));
    const uint32_t cm = __vmaxu2(__vmaxu2(pw[2] & 0x7fff7fffu, pw[3] & 0x7fff7fffu), __byte_perm(ph[2], ph[3], 0x5410) & 0x7fff7fffu);
    const int ex = min(max((int)(__float_as_uint(__uint_as_float(__reduce_max_sync(~0u, max(cm << 16, cm & 0xffff0000u))) * dt) >> 23), 20), 240);
    const float scale = __uint_as_float((uint32_t)(127 + 10 + 127 - ex) << 23), unscale = 2.0f * __uint_as_float((uint32_t)(ex - 10) << 23);
    float k2048 = 0.f;
    float acc[5][4] = {};
    uint32_t af[4][4] = {};
    auto rest = [&] {
        uint32_t b[4][4], c[8];
#pragma unroll
        for (int k = 0; k < 4; k++) {
            ldsm(b[k], ldb ^ (k << 5));
            if (!(k & 1)) ldsm(c + 2 * k, ldc ^ (k << 5));
        }
#pragma unroll
        for (int k = 0; k < 4; k++) { mma(acc[2], af[k], b[k]); mma(acc[3], af[k], b[k] + 2); mma(acc[4], af[k], c + 2 * k); }
    };
#pragma unroll 1
    for (uint32_t sel = 0x1076; sel < (grp < 4 ? 0x6000u : 0x4000u); sel += 0x2200) {
        rest();
        auto par = [&](int i) { return __uint_as_float(__byte_perm(pw[i], ph[i], sel)); };
        const float wr2 = -rbf(expf(par(0))) * dt * 1.4426950408889634f, wi = par(1) * dt;
        const float2 y1 = cexp_at(wr2, -wi, 1.f), w64 = cexp_at(wr2, wi, 64.f), y4 = csqr(csqr(y1)), z8 = csqr(make_float2(y4.x, -y4.y)), y128 = csqr(make_float2(w64.x, -w64.y));
        float2 h0 = make_float2(1.f, 0.f), g0 = make_float2(par(2) * dt * scale, -par(3) * dt * scale);
        const float2 v2 = csqr(y128), v3 = cmul(v2, y128), v4 = csqr(v2), v8 = csqr(v4), c8 = cmul(g0, v8);
        const uint2 z64 = packr(w64), v[8] = {make_uint2(packh(c8), 0u), packr(y128), packr(v2), packr(v3), packr(v4), packr(cmul(v4, y128)), packr(csqr(v3)), packr(cmul(v4, v3))};
        k2048 += fmaf(c8.x, v8.x, -c8.y * v8.y);
        uint32_t ge[4];
#pragma unroll
        for (int e = 0; e < 8; e++) {
            const uint32_t p = packh(h0), q = packh(g0);
            if (!(e & 1)) ge[e >> 1] = q;
            stsm_x4((st1 ^ (e << 4)) + e * 128, p, e ? hcmul(p, z64) : z64.x, q, hcmul(q, v[1]));
            if (e < 7) { h0 = e ? cmul(h0, z8) : z8; g0 = cmul(g0, y1); }
        }
        __syncwarp();
        uint32_t b[4][4];
#pragma unroll
        for (int k = 0; k < 4; k++) { ldsm(af[k], lda ^ (k << 5)); ldsm(b[k], (ldb ^ (k << 5)) + 2048); }
#pragma unroll
        for (int e = 0; e < 8; e += 2) {
            stsm_x4((st2 ^ (e << 4)) + e * 128, hcmul(ge[e & 3], v[2 + (e >> 2)]), hcmul(ge[0], v[4 + (e >> 1)]), hcmul(ge[(e & 3) + 1], v[2 + (e >> 2)]), hcmul(ge[2], v[4 + (e >> 1)]));
            if (!(e & 3)) stsm_x4((st3 ^ (e << 4)) + e * 128, e ? hcmul(v[0].x, v[e]) : v[0].x, hcmul(v[0].x, v[e + 1]), hcmul(v[0].x, v[e + 2]), hcmul(v[0].x, v[e + 3]));
            mma(acc[0], af[e >> 1], b[e >> 1]);
            mma(acc[1], af[e >> 1], b[e >> 1] + 2);
        }
        __syncwarp();
        if (sel == 0x1076) CSK(3);
    }
    rest();
#pragma unroll
    for (int e = 0; e < 5; e++) k2048 += __shfl_xor_sync(~0u, k2048, 1 << e);
    {
        float* Pp = reinterpret_cast<float*>(tab + warp * 256);
        auto sw = [](int i) { return i ^ ((i >> 2) & 24); };
#pragma unroll
        for (int h = 0; h < 2; h++) {
            const int b = g + 8 * h;
            *reinterpret_cast<float2*>(Pp + sw(8 * b + 2 * t)) = make_float2(acc[0][2 * h] * unscale, acc[0][2 * h + 1] * unscale);
            *reinterpret_cast<float2*>(Pp + 128 + sw(8 * b + 2 * t)) = make_float2(acc[1][2 * h] * unscale, acc[1][2 * h + 1] * unscale);
            *reinterpret_cast<float2*>(Pp + 256 + sw(4 * b + 2 * (t & 1) + 64 * (t >> 1))) = make_float2(acc[2][2 * h] * unscale, acc[2][2 * h + 1] * unscale);
            *reinterpret_cast<float2*>(Pp + 384 + sw(2 * b + 32 * t)) = make_float2(acc[3][2 * h] * unscale, acc[3][2 * h + 1] * unscale);
            Pp[512 + sw(b + 32 * t)] = acc[4][2 * h] * unscale;
            Pp[512 + sw(b + 32 * t + 16)] = acc[4][2 * h + 1] * unscale;
        }
        if (lane == 0) Pp[640] = k2048 * unscale;
    }
    CSK(4);
    asm volatile("bar.sync %0, %1;" ::"r"(grp + 4), "r"(grp < 4 ? 64 : 96) : "memory");
    if (warp == 2) return;
    const float* Kp = reinterpret_cast<const float*>(tab);
    auto ksum = [&](int i) -> float { return rbf(Kp[i] + Kp[1024 + i] + (grp < 4 ? 0.f : Kp[2048 + i])); };
    auto ksum2 = [&](int q) -> float2 {
        q ^= (q >> 2) & 12;
        const float2 a = reinterpret_cast<const float2*>(Kp)[q], b = reinterpret_cast<const float2*>(Kp)[512 + q];
        const float2 c = grp < 4 ? make_float2(0.f, 0.f) : reinterpret_cast<const float2*>(Kp)[1024 + q];
        return make_float2(a.x + b.x + c.x, a.y + b.y + c.y);
    };
    {
        uint2* W2 = reinterpret_cast<uint2*>(in.tap + d * (TAPB / 16)) + 8;
        uint2* E4 = W2 + (TAPE - 64) / 8;
        float2 v = ksum2(64 * warp + lane), z = ksum2(64 * warp + 32 + lane), y = ksum2(128 + tid);
        const int q = (96 + tid) ^ (((96 + tid) >> 2) & 6);
        const float4 ua = reinterpret_cast<const float4*>(Kp)[q], uc = reinterpret_cast<const float4*>(Kp)[256 + q], ud = grp < 4 ? make_float4(0.f, 0.f, 0.f, 0.f) : reinterpret_cast<const float4*>(Kp)[512 + q];
        const float4 ub = make_float4(uc.x + ud.x, uc.y + ud.y, uc.z + ud.z, uc.w + ud.w);
        const float s1 = ksum(tid == 31 ? 336 : lane ? 384 : 103), s2 = ksum(tid == 31 ? 512 : tid ? 640 : 231);
        if (tid == 0) v.x += __uint_as_float(kp.pdsk << 16);
        if (tid == 63) y.y -= s1;
        const uint32_t lo = pack2(v.x, v.y), hi = pack2(z.x, z.y), tp = pack2(y.x, y.y);
        uint32_t nl = __shfl_sync(~0u, lo, lane - 1), nh = __shfl_sync(~0u, lane == 31 ? lo : hi, lane - 1), nt = __shfl_sync(~0u, tp, lane + 1);
        if (lane == 0) nl = warp ? __float_as_uint(s1) : 0u;
        if (lane == 31) nt = warp ? 0u : __float_as_uint(s1) >> 16;
        W2[64 * warp + lane] = make_uint2(__byte_perm(lo, nl, 0x7610), __byte_perm(lo, 0, 0x1032));
        W2[64 * warp + lane + 32] = make_uint2(__byte_perm(hi, nh, 0x7610), __byte_perm(hi, 0, 0x1032));
        reinterpret_cast<uint4*>(W2)[64 + tid] = make_uint4(__byte_perm(tp, __float_as_uint(s2), tid ? 0x1010 : 0x7610), __byte_perm(tp, 0, 0x1010), __byte_perm(tp, 0, 0x1032), __byte_perm(nt, tp, 0x7610));
        E4[(tid < 32 ? 159 : 209 - 32) + tid] = make_uint2(pack2(ua.x + ub.x, ua.y + ub.y), pack2(ua.z + ub.z, ua.w + ub.w - (tid == 31 ? s2 : 0.f)));
        if (tid == 63) E4[241] = make_uint2(__float_as_uint(s2) >> 16, 0u);
    }
    CSK(5);
    SPAN(0, 3);
}

#define CV_SLEEP 40
#define CV_TD1 500
#define CV_TD0 0
#define CV_LD "ld.relaxed.gpu.global"
#define CV_NL 1
#define CV_D2 3
#define CV_PDH 12
#define CV_PDF 4
#define CV_HAND 7
constexpr int CV_CPB = 5;
constexpr int CV_THREADS = 512;
constexpr int UPADF = 128;
constexpr int ULEN = UPADF + SEQ;
constexpr int XLEN = XCP;
constexpr int BX_5 = 0, BX_3 = 3264, BX_9 = 6528, BX_7 = 8960, BX_LEN = 11392;
constexpr int CV_SM_U = 0;
constexpr int CV_SM_T = CV_CPB * ULEN * 2;
constexpr int CV_SM_B = CV_SM_T + CV_CPB * TAPB;
constexpr int CV_SM_X = CV_SM_B + CV_CPB * BX_LEN;
constexpr int CV_SM_Y = (CV_SM_X + CV_CPB * XLEN * 2 + 127) & ~127;
constexpr int CV_SM_CNT = CV_SM_Y + CV_CPB * 8192;
constexpr int CV_SM_O = CV_SM_CNT + 128;
constexpr int CV_SMEM = CV_SM_O + 20480 + CST_EXTRA;
static_assert(ULEN % 128 == 0 && CV_SM_B % 128 == 0 && CV_SM_CNT % 128 == 0, "layout");

__device__ __forceinline__ uint32_t sub2(uint32_t x, uint32_t m) {
    const __nv_bfloat162 d = __hsub2(*reinterpret_cast<const __nv_bfloat162*>(&x), *reinterpret_cast<const __nv_bfloat162*>(&m));
    return *reinterpret_cast<const uint32_t*>(&d);
}
__device__ __forceinline__ uint32_t add2(uint32_t x, uint32_t y) {
    const __nv_bfloat162 d = __hadd2_rn(*reinterpret_cast<const __nv_bfloat162*>(&x), *reinterpret_cast<const __nv_bfloat162*>(&y));
    return *reinterpret_cast<const uint32_t*>(&d);
}
__device__ __forceinline__ void wgmma_fence() { asm volatile("wgmma.fence.sync.aligned;" ::: "memory"); }
__device__ __forceinline__ void wgmma_commit() { asm volatile("wgmma.commit_group.sync.aligned;" ::: "memory"); }
template <int N> __device__ __forceinline__ void wgmma_wait() { asm volatile("wgmma.wait_group.sync.aligned %0;" ::"n"(N) : "memory"); }
__device__ __forceinline__ uint64_t make_desc(uint32_t addr, uint32_t lbo, uint32_t sbo, uint32_t mode) {
    return (uint64_t)((addr & 0x3FFFF) >> 4) | ((uint64_t)(lbo >> 4) << 16) | ((uint64_t)(sbo >> 4) << 32) | ((uint64_t)mode << 62);
}
__device__ __forceinline__ void wgmma_rs128(float (&d)[64], uint2 hi, uint2 lo, uint64_t db, int acc) {
    asm volatile("{\n.reg .pred p;\nsetp.ne.b32 p, %69, 0;\nwgmma.mma_async.sync.aligned.m64n128k16.f32.bf16.bf16 {%0,%1,%2,%3,%4,%5,%6,%7,%8,%9,%10,%11,%12,%13,%14,%15,%16,%17,%18,%19,%20,%21,%22,%23,%24,%25,%26,%27,%28,%29,%30,%31,%32,%33,%34,%35,%36,%37,%38,%39,%40,%41,%42,%43,%44,%45,%46,%47,%48,%49,%50,%51,%52,%53,%54,%55,%56,%57,%58,%59,%60,%61,%62,%63}, {%64,%65,%66,%67}, %68, p, 1, 1, 0;\n}"
                 : "+f"(d[0]), "+f"(d[1]), "+f"(d[2]), "+f"(d[3]), "+f"(d[4]), "+f"(d[5]), "+f"(d[6]), "+f"(d[7]), "+f"(d[8]), "+f"(d[9]), "+f"(d[10]), "+f"(d[11]), "+f"(d[12]), "+f"(d[13]), "+f"(d[14]), "+f"(d[15]), "+f"(d[16]), "+f"(d[17]), "+f"(d[18]), "+f"(d[19]), "+f"(d[20]), "+f"(d[21]), "+f"(d[22]), "+f"(d[23]), "+f"(d[24]), "+f"(d[25]), "+f"(d[26]), "+f"(d[27]), "+f"(d[28]), "+f"(d[29]), "+f"(d[30]), "+f"(d[31]), "+f"(d[32]), "+f"(d[33]), "+f"(d[34]), "+f"(d[35]), "+f"(d[36]), "+f"(d[37]), "+f"(d[38]), "+f"(d[39]), "+f"(d[40]), "+f"(d[41]), "+f"(d[42]), "+f"(d[43]), "+f"(d[44]), "+f"(d[45]), "+f"(d[46]), "+f"(d[47]), "+f"(d[48]), "+f"(d[49]), "+f"(d[50]), "+f"(d[51]), "+f"(d[52]), "+f"(d[53]), "+f"(d[54]), "+f"(d[55]), "+f"(d[56]), "+f"(d[57]), "+f"(d[58]), "+f"(d[59]), "+f"(d[60]), "+f"(d[61]), "+f"(d[62]), "+f"(d[63])
                 : "r"(hi.x), "r"(hi.y), "r"(lo.x), "r"(lo.y), "l"(db), "r"(acc));
}
template <int V> struct Int { __device__ constexpr operator int() const { return V; } };
__device__ __forceinline__ void sts4(uint32_t a, const uint32_t* v) { asm volatile("st.shared.v4.u32 [%0], {%1,%2,%3,%4};" ::"r"(a), "r"(v[0]), "r"(v[1]), "r"(v[2]), "r"(v[3]) : "memory"); }
__device__ __forceinline__ uint32_t lds1(uint32_t a) { uint32_t v; asm volatile("ld.shared.u32 %0, [%1];" : "=r"(v) : "r"(a) : "memory"); return v; }
__device__ __forceinline__ uint32_t lds1v(uint32_t a) { uint32_t v; asm volatile("ld.volatile.shared.u32 %0, [%1];" : "=r"(v) : "r"(a) : "memory"); return v; }
__device__ __forceinline__ uint4 lds4(uint32_t a) { uint4 v; asm volatile("ld.shared.v4.u32 {%0,%1,%2,%3}, [%4];" : "=r"(v.x), "=r"(v.y), "=r"(v.z), "=r"(v.w) : "r"(a) : "memory"); return v; }
__device__ __forceinline__ uint4 ldx(uint32_t a) {
    uint4 v;
    asm volatile("ld.shared.v2.u32 {%0,%1}, [%4];\nld.shared.v2.u32 {%2,%3}, [%4+128];" : "=r"(v.x), "=r"(v.y), "=r"(v.z), "=r"(v.w) : "r"(a) : "memory");
    return v;
}
__device__ __forceinline__ void cv_store(unsigned char* p, uint4 x, uint4 y) {
    asm volatile("st.relaxed.gpu.global.v2.u32 [%0], {%1,%2};" ::"l"(p), "r"(add2(x.x, __byte_perm(y.x, y.y, 0x5410))), "r"(add2(x.y, __byte_perm(y.z, y.w, 0x5410))) : "memory");
    asm volatile("st.relaxed.gpu.global.v2.u32 [%0], {%1,%2};" ::"l"(p + 128), "r"(add2(x.z, __byte_perm(y.x, y.y, 0x7632))), "r"(add2(x.w, __byte_perm(y.z, y.w, 0x7632))) : "memory");
}
__device__ __forceinline__ int usw(int ch) { return ch ^ ((ch >> 3) & 1); }
__global__ void __launch_bounds__(CV_THREADS, 1) conv_kernel(int layer, const uint4* __restrict__ piv, const float4* __restrict__ sum, const bf16* __restrict__ x1T,
                                                             bf16* __restrict__ dst, const uint4* __restrict__ tap, const __grid_constant__ CUtensorMap tmOut) {
    extern __shared__ __align__(1024) unsigned char sm[];
    SPAN(3 + 4 * layer, 0);
    bf16* Us = reinterpret_cast<bf16*>(sm + CV_SM_U);
    bf16* Xs = reinterpret_cast<bf16*>(sm + CV_SM_X);
#define CV_IDX int tid; asm volatile("mov.u32 %0, %tid.x;" : "=r"(tid)); const int lane = tid & 31, warp = __shfl_sync(~0u, tid >> 5, 0);
    const int d0 = blockIdx.x * CV_CPB, tile = blockIdx.x; (void)tile;
    const uint32_t cnt = smem_u32(sm + CV_SM_CNT);
    struct Lc { uint32_t a4, a8, uc, ud, y, e4, en, sp, ss; int go; };
    auto lane_consts = [&](int lane, int c) {
        const int mat = lane >> 3, r = lane & 7, g = lane >> 2, ti = lane & 3, e = g - 2 * ti;
        const int j2 = 13 + (r ^ 1) + 8 * (mat >> 1), j3 = j2 + 2, i0 = 8 * (mat & 1);
        const uint32_t sb = smem_u32(sm), oc = sb + usw(16 * (mat >> 1) + 2 * r + (mat & 1)) * 16;
        const Lc l = {sb + CV_SM_B + c * BX_LEN + ((j2 & 1) ? BX_3 + (4 * j2 + i0 + 84) * 2 : BX_5 + (4 * j2 + i0 + 80) * 2),
                      sb + CV_SM_B + c * BX_LEN + ((j3 & 1) ? BX_7 : BX_9) + (8 * j3 + i0 + 136) * 2,
                      oc + CV_SM_U + (c * ULEN + UPADF) * 2, sb + CV_SM_U + (c * ULEN + UPADF) * 2 + usw(16 * mat + 2 * r + 2) * 16, oc + CV_SM_Y + c * 8192,
                      sb + CV_SM_T + c * TAPB + TAPE + (307 + 2 * g - ti) * 4, sb + CV_SM_T + c * TAPB + (528 + e) * 4,
                      e == -5 ? 0x4410u : e == -4 ? 0x1044u : 0x4444u, e == 3 ? 0x4410u : e == 4 ? 0x1044u : 0x4444u,
                      c * XCP * 2 + (lane >> 4) * 256 + (lane & 15) * 8};
        asm volatile("st.shared.u32 [%0], %1;" ::"r"(sb + CV_SM_CNT + 120), "r"(l.y ^ l.a4 ^ l.a8 ^ l.uc ^ l.ud ^ l.e4 ^ l.en ^ l.sp ^ l.ss ^ l.go) : "memory");
        return l;
    };
    unsigned char* const dq = reinterpret_cast<unsigned char*>(dst + (size_t)d0 * XCP);
    auto far = [&](auto T0_, const auto& seq, const Lc& lc, int c, int lane, const uint2 (&f)[20], uint32_t kk) {
        constexpr int T0 = T0_, T1 = T0 + 6, TC = T0 > 7 ? T0 : 7, NS = sizeof(seq) / sizeof(seq[0]), PD = T0 > 7 ? CV_PDH : CV_PDF;
        uint32_t bq[28], yw[4], yz[4], P, S;
        uint4 xv, yv;
        asm("prmt.b32 %0, %1, 0, %2;" : "=r"(P) : "r"(kk), "r"(lc.sp));
        asm("prmt.b32 %0, %1, 0, %2;" : "=r"(S) : "r"(kk), "r"(lc.ss));
#pragma unroll
        for (int k = 0; 2 * k < T1 - TC + 4; k++) ldsm_x4(bq + 4 * k, lc.uc + (TC - 8) * 256 + 512 * k);
#pragma unroll
        for (int k = 0; 4 * k < T1 - TC; k++) ldsm_x4(bq + 20 + 4 * k, lc.ud + (TC - 8) * 256 + 1024 * k);
        CST(3);
        mbar_wait(cnt + 8 * c, 0);
        mbar_wait(cnt + 40, 0);
        CST(4);
        float acc[6][4] = {};
        uint32_t a[PD + 1][4];
#pragma unroll
        for (int i = -PD; i < NS + 3; i++) {
            if (i + PD < NS) ldsm_x4_t(a[(i + PD) % (PD + 1)], seq[i + PD] < 32 ? lc.a4 + (seq[i + PD] - 2) * 128 : lc.a8 + (seq[i + PD] - 34) * 256);
            if (i < 0) continue;
#pragma unroll
            for (int T = T0; T < T1; T++) {
                if (i >= NS) break;
                const int ee = seq[i] < 32 ? 2 * T - 6 - seq[i] : T + 35 - seq[i];
                if (i == 0 && T >= TC) mma_bf16(acc[T - T0], P, 0u, S, P, bq[2 * (T - TC)], bq[2 * (T - TC) + 1]);
                if (i == 1 && T >= TC) mma_bf16_k8(acc[T - T0], 0u, S, bq[20 + T - TC]);
                if (i == (T >= TC ? 2 : 0)) mma_bf16(acc[T - T0], f[19].x, 0u, f[19].y, f[19].x, bq[2 * (T - TC + 4)], bq[2 * (T - TC + 4) + 1]);
                if (seq[i] < 32 ? ee >= 0 && ee <= 9 : ee >= 10) mma_bf16(acc[T - T0], a[i % (PD + 1)][0], a[i % (PD + 1)][1], a[i % (PD + 1)][2], a[i % (PD + 1)][3], f[ee].x, f[ee].y);
            }
#pragma unroll
            for (int k = 0; k < 3; k++) {
                const int o = 256 * T0 + 512 * k;
                auto at = [&](int d) { return i - d >= 0 && i - d < NS && seq[i - d < 0 ? 0 : i - d < NS ? i - d : 0] == 2 * T0 + 4 * k - 4; };
                if (at(CV_D2)) {
                    cv_store(dq + lc.go + o, xv, yv);
                    if (layer > 19 - 2 * k) __trap();
                }
                if (at(-2)) { ldsm_x4_t(yw, lc.y + o); ldsm_x4_t(yz, lc.y + 3584 + o); }
                if (at(1)) {
#pragma unroll
                    for (int q = 0; q < 4; q++) yw[q] = add2(add2(yw[q], yz[q]), pack2(acc[2 * k + (q >> 1)][2 * (q & 1)], acc[2 * k + (q >> 1)][2 * (q & 1) + 1]));
                    stsm_x4_t(lc.y + o, yw[0], yw[1], yw[2], yw[3]);
                    xv = ldx(smem_u32(Xs) + lc.go + o);
                    __syncwarp();
                    yv = lds4(smem_u32(sm + CV_SM_Y) + c * 8192 + o + usw(lane) * 16);
                    if (layer > 20 - 2 * k) __trap();
                    if (k == 2) CST(6);
                }
            }
        }
    };
    TSTAMP1X(9, 256);
    if (threadIdx.x >= 256) {
        if (threadIdx.x < 288 && elect()) {
            mbar_init(cnt + 48, 1);
            asm volatile("fence.mbarrier_init.release.cluster;" ::: "memory");
            bulk_load(smem_u32(sm + CV_SM_T), tap + d0 * (TAPB / 16), CV_CPB * TAPB, cnt + 48);
            mbar_expect_tx(cnt + 48, CV_CPB * TAPB);
        }
        CV_IDX
        const int wgu = (warp >> 2) & 1, g = lane >> 2, ti = lane & 3;
        CST(1);
        if (warp > 8 && elect()) {
            if (warp < 15) mbar_init(cnt + 8 * (warp - 9), warp == 14 ? 8 : 4);
            else if (layer) prefetch_tmap(&tmOut);
        }
        if (warp < 13 && lane < 17 - (warp == 12)) {
            const int off = warp == 12 ? CV_SM_U : CV_SM_B + (warp == 11 ? BX_7 : (warp - 8) * BX_3), str = warp == 12 ? ULEN * 2 : BX_LEN;
#pragma unroll
            for (int c = 0; c < CV_CPB; c++) *reinterpret_cast<uint4*>(sm + off + c * str + 16 * lane) = make_uint4(0, 0, 0, 0);
        }
        fence_async_smem();
        asm volatile("bar.arrive 3, 512;" ::: "memory");
        asm volatile("bar.sync 1, 256;" ::: "memory");
        TSTAMP1X(10, 256);
        asm volatile("setmaxnreg.inc.sync.aligned.u32 168;");
        const uint32_t Tc = smem_u32(sm + CV_SM_T) + (16 + 128 * (warp & 2) + 8 * (warp & 1) + g - 2 * ti) * 4;
        uint2 fa[8][2], fn[8][2];
        auto near_taps = [&](uint2 (&f)[8][2], int c) {
#pragma unroll
            for (int m = 0; m < 16; m++) f[m >> 1][m & 1] = make_uint2(lds1v(Tc + c * TAPB + 64 * (m >> 1) - 32 * (m & 1)), lds1v(Tc + c * TAPB + 64 * (m >> 1) - 32 * (m & 1) + 512));
        };
        CST(6);
        mbar_wait(cnt + 48, 0);
        TSTAMP1X(11, 256); CST(5);
        near_taps(fa, 3 * wgu);
        near_taps(fn, 2 - wgu);
        const int hc = wgu ? warp & 3 : 4;
        const Lc lc = lane_consts(lane, hc);
        TSTAMP1X(12, 256); CST(0);
        uint32_t ya = smem_u32(sm + CV_SM_Y) + wgu * 8192 + (warp & 2) * 2048 + usw(2 * lane + (warp & 1)) * 16;
        uint64_t db = make_desc(smem_u32(Us + wgu * ULEN + UPADF), 16, 256, 3);
        if (wgu) asm volatile("bar.sync 6, 384;" ::: "memory");
        int c = wgu;
        auto chain = [&](const uint2 (&f)[8][2], auto&& meanwhile) {
            float acc[64];
            asm volatile("bar.sync %0, %1;" ::"r"(c ? 4 + wgu : 2), "r"(c ? 256 : 384) : "memory");
            TSTAMPC(1 + 3 * c);
            if (c < 2) CST(7);
            if (c == 0) fence_async_smem();
            wgmma_fence();
#pragma unroll
            for (int m = 0; m < 8; m++) {
                wgmma_rs128(acc, f[m][0], f[m][1], db - (uint64_t)(2 * m), m);
                if (m == CV_HAND && c < 4) asm volatile("bar.arrive %0, 256;" ::"r"(5 - wgu) : "memory");
            }
            wgmma_commit();
            asm volatile("griddepcontrol.launch_dependents;" ::: "memory");
            TSTAMPC(2 + 3 * c); CST(13 + (c >> 1));
            meanwhile();
            wgmma_wait<0>();
            TSTAMPC(3 + 3 * c); CST(10 + (c >> 1));
            uint32_t w[16];
#pragma unroll
            for (int j = 0; j < 16; j++) w[j] = j ? pack2(acc[4 * j] + acc[4 * j - 2], acc[4 * j + 1] + acc[4 * j - 1]) : pack2(acc[0], acc[1]);
#pragma unroll
            for (int j = 0; j < 16; j += 4) stsm_x4_t(ya + 256 * j, w[j], w[j + 1], w[j + 2], w[j + 3]);
            __syncwarp();
            if (lane == 0) mbar_arrive(cnt + 8 * c);
            c += 2; ya += 16384; db += ULEN / 4;
        };
        const uint32_t e4 = lc.e4, e8 = e4 + 428 - 4 * g;
        uint2 fl[4];
        uint32_t kk;
#pragma unroll 1
        for (;;) {
            if (c != 1) chain(fa, [&] {
                if (c == 3 || warp + c == 12) {
#pragma unroll
                    for (int k = 0; k < 19; k++) (k < 16 ? fn[(k >> 1) & 7][k & 1] : fl[k & 3]) = make_uint2(lds1(k < 10 ? e4 + 32 * k + 16 : e8 + 32 * k - 304), lds1(k < 10 ? e4 + 32 * k : e8 + 32 * k - 320));
                    fl[3] = make_uint2(lds1(lc.en), lds1(lc.en - 32));
                    kk = lds1(smem_u32(sm + CV_SM_T) + TAPB * hc + TAPE + 1672);
                }
            });
            if (c > 4) break;
            if (c == 2) { asm volatile("bar.sync 7, 384;" ::: "memory"); fence_async_smem(); }
            chain(fn, [&] { if (c == 2) near_taps(fa, 4); });
        }
        TSTAMP1X(6, 256); CST(2);
        if (wgu || warp == 8) {
            constexpr int seq[29] = {5, 6, 32, 7, 33, 8, 34, 9, 35, 10, 36, 11, 12, 13, 14, 15, 16, 17, 37, 18, 38, 19, 20, 21, 39, 22, 40, 23, 24};
            uint2 f[20];
#pragma unroll
            for (int k = 0; k < 20; k++) f[k] = k < 16 ? fn[(k >> 1) & 7][k & 1] : fl[k & 3];
            far(Int<10>(), seq, lc, hc, lane, f, kk);
        }
    } else {
        asm volatile("setmaxnreg.dec.sync.aligned.u32 88;");
        CV_IDX
        CST(5);
        const uint4* ppv = piv + tid;
        const float4* psv = sum + tid;
        const uint2* pxv = reinterpret_cast<const uint2*>(x1T + (size_t)d0 * XCP) + (tid >> 4) * 32 + (tid & 15);
        asm volatile("st.shared.u64 [%0], %1;" ::"r"(smem_u32(sm + CV_SM_O) + tid * 16), "l"((uint64_t)ppv ^ (uint64_t)psv ^ (uint64_t)pxv) : "memory");
        const int tc = (0x04302100 >> (4 * warp)) & 7;
        const Lc lc = lane_consts(lane, tc);
        pdl_sync();
        SPAN(3 + 4 * layer, 1);
        TSTAMP(0); CST(0);
        if (tid == 0) TSTAMPC(0);
        if (threadIdx.x == 0) { GSTAMP(g_tim, 15); }
        float4 sv[4];
        uint4 pv;
#pragma unroll
        for (int k = 0; k < 4; k++)
            asm volatile(CV_LD ".v4.f32 {%0,%1,%2,%3}, [%4];" : "=f"(sv[k].x), "=f"(sv[k].y), "=f"(sv[k].z), "=f"(sv[k].w) : "l"(psv + 256 * k) : "memory");
        asm volatile(CV_LD ".v4.u32 {%0,%1,%2,%3}, [%4];" : "=r"(pv.x), "=r"(pv.y), "=r"(pv.z), "=r"(pv.w) : "l"(ppv) : "memory");
        uint2 xe[CV_CPB], xo[CV_CPB];
#pragma unroll
        for (int c = 0; c < CV_NL; c++) {
            asm volatile(CV_LD ".v2.u32 {%0,%1}, [%2];" : "=r"(xe[c].x), "=r"(xe[c].y) : "l"(pxv + c * (XCP / 4)) : "memory");
            asm volatile(CV_LD ".v2.u32 {%0,%1}, [%2];" : "=r"(xo[c].x), "=r"(xo[c].y) : "l"(pxv + c * (XCP / 4) + 16) : "memory");
        }
#define CV_XD 60
#define CV_XW 0
        if (warp == CV_XW) {
            if (elect()) {
                mbar_init(cnt + 56, 1);
                asm volatile("fence.mbarrier_init.release.cluster;" ::: "memory");
                mbar_expect_tx(cnt + 56, CV_CPB * 4096);
                pause(CV_XD);
#pragma unroll
                for (int c = CV_NL; c < CV_CPB + CV_NL; c++) bulk_load(smem_u32(Xs + (c % CV_CPB) * XLEN), x1T + (size_t)(d0 + c % CV_CPB) * XCP, 4096, cnt + 56);
            }
            __syncwarp();
            CST(15);
        }
        uint32_t mw[4];
        float rs[8];
#pragma unroll
        for (int k = 0; k < 4; k++) {
            const uint32_t pw = k == 0 ? pv.x : k == 1 ? pv.y : k == 2 ? pv.z : pv.w;
            uint32_t vr;
            mw[k] = pack2(sv[k].x + __uint_as_float(pw << 16), sv[k].z + __uint_as_float(pw & 0xffff0000u));
            asm("cvt.rn.relu.bf16x2.f32 %0, %1, %2;" : "=r"(vr) : "f"(fmaf(-sv[k].z, sv[k].z, sv[k].w)), "f"(fmaf(-sv[k].x, sv[k].x, sv[k].y)));
            const uint32_t ve = pack2(__uint_as_float(vr << 16) + 1e-5f, __uint_as_float(vr & 0xffff0000u) + 1e-5f);
            const uint32_t sd = pack2(sqrt_apx(__uint_as_float(ve << 16)), sqrt_apx(__uint_as_float(ve & 0xffff0000u)));
            rs[2 * k] = rcp_apx(__uint_as_float(sd << 16)); rs[2 * k + 1] = rcp_apx(__uint_as_float(sd & 0xffff0000u));
        }
        if (rs[0] != 123.f) TSTAMP(13);
        const uint32_t ua = smem_u32(Us) + usw(tid + UPADF / 8) * 16;
        uint32_t uw[CV_CPB][4];
#pragma unroll
        for (int c = 0; c < CV_CPB; c++) {
            if (c == CV_NL) {
                if (warp == CV_XW) { mbar_wait(cnt + 56, 0); CST(7); }
                asm volatile("bar.sync 10, 256;" ::: "memory");
            }
            if (c == 1 || c == 2) {
#pragma unroll
                for (int k = c; k < (c == 1 ? 2 : CV_CPB); k++) {
 const uint4 v = ldx(smem_u32(Xs + k * XLEN) + (tid >> 4) * 256 + (tid & 15) * 8); xe[k] = make_uint2(v.x, v.y); xo[k] = make_uint2(v.z, v.w); }
            }
            const uint32_t e0 = sub2(xe[c].x, mw[0]), e1 = sub2(xe[c].y, mw[1]), o0 = sub2(xo[c].x, mw[2]), o1 = sub2(xo[c].y, mw[3]);
            uw[c][0] = pack2(__uint_as_float(e0 << 16) * rs[0], __uint_as_float(o0 << 16) * rs[4]); uw[c][1] = pack2(__uint_as_float(e0 & 0xffff0000u) * rs[1], __uint_as_float(o0 & 0xffff0000u) * rs[5]);
            uw[c][2] = pack2(__uint_as_float(e1 << 16) * rs[2], __uint_as_float(o1 << 16) * rs[6]); uw[c][3] = pack2(__uint_as_float(e1 & 0xffff0000u) * rs[3], __uint_as_float(o1 & 0xffff0000u) * rs[7]);
            asm volatile("st.shared.v4.u32 [%0], {%1,%2,%3,%4};" ::"r"(ua + c * ULEN * 2), "r"(uw[c][0]), "r"(uw[c][1]), "r"(uw[c][2]), "r"(uw[c][3]) : "memory");
            if (c < 2) {
                if (c == 1) fence_async_smem();
                asm volatile("bar.arrive %0, 384;" ::"r"(2 + 4 * c) : "memory");
                if (layer > 29 - c) __trap();
                CST(11 + c);
            }
        }
        asm volatile("bar.arrive 7, 384;" ::: "memory");
        asm volatile("bar.sync 3, 512;" ::: "memory");
        TSTAMP(1); CST(1);
        {
            auto box = [&](auto c0, auto c1, int chunk, int cb, bool full) {
                const uint32_t ea = smem_u32(Us + cb * ULEN) + usw(chunk + UPADF / 8 + (lane ? 1 : -1)) * 16, bx = smem_u32(sm + CV_SM_B + cb * BX_LEN) + chunk * 16;
                uint32_t lo[CV_CPB][4], hi[CV_CPB][2];
#pragma unroll
                for (int c = c0; c < c1; c++) {
                    lo[c][0] = 0;
#pragma unroll
                    for (int k = 1; k < 4; k++) lo[c][k] = __shfl_up_sync(~0u, uw[c][k], 1);
#pragma unroll
                    for (int k = 0; k < 2; k++) hi[c][k] = __shfl_down_sync(~0u, uw[c][k], 1);
                }
#pragma unroll
                for (int c = c0; c < c1; c++)
                    asm volatile("{\n.reg .pred p, q;\nsetp.eq.s32 p, %7, 0;\nsetp.eq.s32 q, %7, 31;\n@p ld.shared.v4.u32 {%0,%1,%2,%3}, [%6];\n@q ld.shared.v2.u32 {%4,%5}, [%6];\n}"
                                 : "+r"(lo[c][0]), "+r"(lo[c][1]), "+r"(lo[c][2]), "+r"(lo[c][3]), "+r"(hi[c][0]), "+r"(hi[c][1]) : "r"(ea + c * ULEN * 2), "r"(lane) : "memory");
#pragma unroll
                for (int c = c0; c < c1; c++) {
                    const uint32_t e[9] = {lo[c][1], lo[c][2], lo[c][3], uw[c][0], uw[c][1], uw[c][2], uw[c][3], hi[c][0], hi[c][1]};
                    uint32_t o[8], p[8], t[7], b3[5], b5[7];
#pragma unroll
                    for (int i = 0; i < 8; i++) { o[i] = __byte_perm(e[i], e[i + 1], 0x5432); p[i] = add2(e[i], o[i]); }
#pragma unroll
                    for (int i = 0; i < 5; i++) b3[i] = add2(o[i], p[i + 1]);
                    sts4(bx + c * BX_LEN + BX_3 + 160, b3);
#pragma unroll
                    for (int i = 1; i < 7; i++) { t[i] = add2(p[i], p[i + 1]); b5[i] = add2(t[i], e[i + 2]); }
                    sts4(bx + c * BX_LEN + BX_5 + 160, b5 + 2);
                    if (full) {
#pragma unroll
                        for (int i = 1; i < 5; i++) { b3[i] = add2(b3[i], t[i + 2]); t[i] = add2(t[i], b5[i + 2]); }
                        sts4(bx + c * BX_LEN + BX_7 + 272, b3 + 1);
                        sts4(bx + c * BX_LEN + BX_9 + 272, t + 1);
                    }
                }
            };
            auto reload = [&](int c, uint32_t a) { const uint4 v = lds4(a); uw[c][0] = v.x; uw[c][1] = v.y; uw[c][2] = v.z; uw[c][3] = v.w; };
            if (warp >= 6) {
#pragma unroll
                for (int c = 0; c < 3; c++) reload(c, ua - 1024 + (c + 2) * ULEN * 2);
            }
            if (warp >= 4) {
#pragma unroll
                for (int c = 3; c < 5; c++) reload(c, ua - 2048 + c * ULEN * 2);
            }
            box(Int<0>(), Int<3>(), warp < 6 ? tid : tid - 64, warp < 6 ? 0 : 2, warp < 4);
            if (warp >= 4) box(Int<3>(), Int<5>(), tid - 128, 0, true);
            else if (tid >= 128 - CV_CPB) {
                const int c = 127 - tid;
                const uint2 v = *reinterpret_cast<const uint2*>(Us + c * ULEN + UPADF);
                const float s1 = __uint_as_float(v.x << 16), s2 = s1 + __uint_as_float(v.x & 0xffff0000u), s3 = s2 + __uint_as_float(v.y << 16), s4 = s3 + __uint_as_float(v.y & 0xffff0000u);
                unsigned char* bc = sm + CV_SM_B + c * BX_LEN;
                *reinterpret_cast<uint32_t*>(bc + BX_5 + 156) = pack2(s1, s2);
                *reinterpret_cast<uint2*>(bc + BX_7 + 264) = make_uint2(v.x << 16, pack2(s2, s3));
                *reinterpret_cast<uint2*>(bc + BX_9 + 264) = make_uint2(pack2(s1, s2), pack2(s3, s4));
            }
        }
        __syncwarp();
        if (lane == 0) mbar_arrive(cnt + 40);
        TSTAMP(2); CST(2);
        if (layer && blockIdx.x == 0 && tid == 224) g_epoch = ld_epoch();
        __syncwarp();
        if ((0x6e >> warp) & 1) {
            constexpr int seq[16] = {0, 1, 2, 3, 4, 5, 6, 32, 7, 8, 9, 33, 10, 34, 11, 12};
            uint2 f[20];
            mbar_wait(cnt, 0);
            const uint32_t e8 = lc.e4 + 428 - (lane & 28);
#pragma unroll
            for (int k = 0; k < 13; k++) f[k] = make_uint2(lds1(k < 10 ? lc.e4 + 32 * k + 16 : e8 + 32 * k - 304), lds1(k < 10 ? lc.e4 + 32 * k : e8 + 32 * k - 320));
            f[19] = make_uint2(lds1(lc.en), lds1(lc.en - 32));
            far(Int<4>(), seq, lc, tc, lane, f, lds1(smem_u32(sm + CV_SM_T) + TAPB * tc + TAPE + 1672));
        }
    }
    {
        CV_IDX
        if ((0xc91 >> warp) & 1) {
            const int c = __popc(0xc91 & ((1 << warp) - 1));
            uint4 xv[2], yv[2];
#pragma unroll
            for (int k = 0; k < 2; k++) xv[k] = ldx(smem_u32(Xs + c * XLEN) + 512 * k + (lane >> 4) * 256 + (lane & 15) * 8);
            const uint32_t u0 = lds1(smem_u32(Us + c * ULEN) + (lane == 31 ? UPADF * 2 : 0));
            mbar_wait(cnt + 8 * c, 0);
#pragma unroll
            for (int k = 0; k < 2; k++) yv[k] = lds4(smem_u32(sm + CV_SM_Y) + c * 8192 + 512 * k + usw(lane) * 16);
            const uint4 yz = lds4(smem_u32(sm + CV_SM_Y) + c * 8192 + 4096 + usw(lane) * 16);
            const float kk = __uint_as_float(lds1(smem_u32(sm + CV_SM_T) + TAPB * c + TAPE + 1272) << 16);
            yv[1].x = add2(yv[1].x, yz.x); yv[1].y = add2(yv[1].y, yz.y); yv[1].z = add2(yv[1].z, yz.z);
            yv[1].w = pack2(fmaf(kk, __uint_as_float(u0 << 16), __uint_as_float(yv[1].w << 16) + __uint_as_float(yz.w << 16)),
                            fmaf(kk, __uint_as_float(u0 << 16) + __uint_as_float(u0 & 0xffff0000u), __uint_as_float(yv[1].w & 0xffff0000u) + __uint_as_float(yz.w & 0xffff0000u)));
#pragma unroll
            for (int k = 0; k < 2; k++) cv_store(dq + c * XCP * 2 + (lane >> 4) * 256 + (lane & 15) * 8 + 512 * k, xv[k], yv[k]);
        }
        TSTAMP(4); CST(8);
        if (layer == 1) {
            const int rb = (blockIdx.x >> 3) + (warp & 8) * 2, cg = blockIdx.x & 7, ch = (tid >> 3) & 31;
            const bf16* src = dst + (size_t)(cg * 80 + ch) * XCP + rb * 64 + (tid & 7) * 8;
            uint32_t v[3][4];
            __syncthreads();
            pause(warp & 8 ? CV_TD1 : CV_TD0);
            uint32_t todo = (warp & 4) ? 3 : 7;
#pragma unroll 1
            for (int it = 0; it < SPIN_MAX; it++) {
#pragma unroll
                for (int k = 0; k < 3; k++)
                    if (todo >> k & 1)
                        asm volatile("ld.relaxed.gpu.global.v4.u32 {%0,%1,%2,%3}, [%4];" : "=r"(v[k][0]), "=r"(v[k][1]), "=r"(v[k][2]), "=r"(v[k][3]) : "l"(src + k * (32 * XCP)) : "memory");
#pragma unroll
                for (int k = 0; k < 3; k++)
                    if ((todo >> k & 1) && v[k][0] != ~0u && v[k][1] != ~0u && v[k][2] != ~0u && v[k][3] != ~0u) {
                        *reinterpret_cast<uint4*>(sm + (32 * k + ch) * 272 + ((tid & 7) + (warp & 8)) * 16) = make_uint4(v[k][0], v[k][1], v[k][2], v[k][3]);
                        todo ^= 1u << k;
                    }
                if (!todo) break;
                __nanosleep(CV_SLEEP);
            }
            __syncwarp();
            asm volatile("bar.sync %0, 256;" ::"r"(8 + (warp >> 3)) : "memory");
            uint32_t w[12];
#pragma unroll
            for (int k = 0; k < 3; k++) ldsm_x4(&w[4 * k], smem_u32(sm) + min(32 * k + lane, 79) * 272 + warp * 16);
            const uint32_t ot = smem_u32(sm + CV_SM_O) + warp * 1280, oa = ot + (lane & 7) * 160 + (lane >> 3) * 16;
            stsm_x4_t(oa, w[0], w[1], w[2], w[3]);
            stsm_x4_t(oa + 64, w[4], w[5], w[6], w[7]);
            asm volatile("stmatrix.sync.aligned.m8n8.x2.trans.shared.b16 [%0], {%1,%2};" ::"r"(oa + 128), "r"(w[8]), "r"(w[9]) : "memory");
            fence_async_smem();
            __syncwarp();
            if (lane == 0) {
                asm volatile("cp.async.bulk.tensor.3d.global.shared::cta.bulk_group [%0, {%1, %2, %3}], [%4];" ::"l"(&tmOut), "r"(cg * 80), "r"((rb >> 1) * 64 + 8 * (warp & 7)), "r"(rb & 1), "r"(ot) : "memory");
                asm volatile("cp.async.bulk.commit_group;" ::: "memory");
                asm volatile("cp.async.bulk.wait_group.read 0;" ::: "memory");
            }
        }
    }
    TSTAMP(3); CST(9); CST_END;
    GSTAMP(g_tim, 14);
    SPAN(3 + 4 * layer, 3);
}

template <int TA, int TB>
__device__ __forceinline__ void wgmma_n240(float (&d)[120], uint64_t da, uint64_t db, int acc) {
    asm volatile("{\n.reg .pred p;\nsetp.ne.b32 p, %124, 0;\nwgmma.mma_async.sync.aligned.m64n240k16.f32.bf16.bf16 {%0,%1,%2,%3,%4,%5,%6,%7,%8,%9,%10,%11,%12,%13,%14,%15,%16,%17,%18,%19,%20,%21,%22,%23,%24,%25,%26,%27,%28,%29,%30,%31,%32,%33,%34,%35,%36,%37,%38,%39,%40,%41,%42,%43,%44,%45,%46,%47,%48,%49,%50,%51,%52,%53,%54,%55,%56,%57,%58,%59,%60,%61,%62,%63,%64,%65,%66,%67,%68,%69,%70,%71,%72,%73,%74,%75,%76,%77,%78,%79,%80,%81,%82,%83,%84,%85,%86,%87,%88,%89,%90,%91,%92,%93,%94,%95,%96,%97,%98,%99,%100,%101,%102,%103,%104,%105,%106,%107,%108,%109,%110,%111,%112,%113,%114,%115,%116,%117,%118,%119}, %120, %121, p, 1, 1, %122, %123;\n}"
                 : "+f"(d[0]), "+f"(d[1]), "+f"(d[2]), "+f"(d[3]), "+f"(d[4]), "+f"(d[5]), "+f"(d[6]), "+f"(d[7]), "+f"(d[8]), "+f"(d[9]), "+f"(d[10]), "+f"(d[11]), "+f"(d[12]), "+f"(d[13]), "+f"(d[14]), "+f"(d[15]), "+f"(d[16]), "+f"(d[17]), "+f"(d[18]), "+f"(d[19]), "+f"(d[20]), "+f"(d[21]), "+f"(d[22]), "+f"(d[23]), "+f"(d[24]), "+f"(d[25]), "+f"(d[26]), "+f"(d[27]), "+f"(d[28]), "+f"(d[29]), "+f"(d[30]), "+f"(d[31]), "+f"(d[32]), "+f"(d[33]), "+f"(d[34]), "+f"(d[35]), "+f"(d[36]), "+f"(d[37]), "+f"(d[38]), "+f"(d[39]), "+f"(d[40]), "+f"(d[41]), "+f"(d[42]), "+f"(d[43]), "+f"(d[44]), "+f"(d[45]), "+f"(d[46]), "+f"(d[47]), "+f"(d[48]), "+f"(d[49]), "+f"(d[50]), "+f"(d[51]), "+f"(d[52]), "+f"(d[53]), "+f"(d[54]), "+f"(d[55]), "+f"(d[56]), "+f"(d[57]), "+f"(d[58]), "+f"(d[59]), "+f"(d[60]), "+f"(d[61]), "+f"(d[62]), "+f"(d[63]), "+f"(d[64]), "+f"(d[65]), "+f"(d[66]), "+f"(d[67]), "+f"(d[68]), "+f"(d[69]), "+f"(d[70]), "+f"(d[71]), "+f"(d[72]), "+f"(d[73]), "+f"(d[74]), "+f"(d[75]), "+f"(d[76]), "+f"(d[77]), "+f"(d[78]), "+f"(d[79]), "+f"(d[80]), "+f"(d[81]), "+f"(d[82]), "+f"(d[83]), "+f"(d[84]), "+f"(d[85]), "+f"(d[86]), "+f"(d[87]), "+f"(d[88]), "+f"(d[89]), "+f"(d[90]), "+f"(d[91]), "+f"(d[92]), "+f"(d[93]), "+f"(d[94]), "+f"(d[95]), "+f"(d[96]), "+f"(d[97]), "+f"(d[98]), "+f"(d[99]), "+f"(d[100]), "+f"(d[101]), "+f"(d[102]), "+f"(d[103]), "+f"(d[104]), "+f"(d[105]), "+f"(d[106]), "+f"(d[107]), "+f"(d[108]), "+f"(d[109]), "+f"(d[110]), "+f"(d[111]), "+f"(d[112]), "+f"(d[113]), "+f"(d[114]), "+f"(d[115]), "+f"(d[116]), "+f"(d[117]), "+f"(d[118]), "+f"(d[119])
                 : "l"(da), "l"(db), "n"(TA), "n"(TB), "r"(acc));
}

__device__ __forceinline__ void wgmma_n80(float (&d)[40], uint64_t da, uint64_t db, int acc) {
    asm volatile("{\n.reg .pred p;\nsetp.ne.b32 p, %42, 0;\nwgmma.mma_async.sync.aligned.m64n80k16.f32.bf16.bf16 {%0,%1,%2,%3,%4,%5,%6,%7,%8,%9,%10,%11,%12,%13,%14,%15,%16,%17,%18,%19,%20,%21,%22,%23,%24,%25,%26,%27,%28,%29,%30,%31,%32,%33,%34,%35,%36,%37,%38,%39}, %40, %41, p, 1, 1, 0, 1;\n}"
                 : "+f"(d[0]), "+f"(d[1]), "+f"(d[2]), "+f"(d[3]), "+f"(d[4]), "+f"(d[5]), "+f"(d[6]), "+f"(d[7]), "+f"(d[8]), "+f"(d[9]), "+f"(d[10]), "+f"(d[11]), "+f"(d[12]), "+f"(d[13]), "+f"(d[14]), "+f"(d[15]), "+f"(d[16]), "+f"(d[17]), "+f"(d[18]), "+f"(d[19]), "+f"(d[20]), "+f"(d[21]), "+f"(d[22]), "+f"(d[23]), "+f"(d[24]), "+f"(d[25]), "+f"(d[26]), "+f"(d[27]), "+f"(d[28]), "+f"(d[29]), "+f"(d[30]), "+f"(d[31]), "+f"(d[32]), "+f"(d[33]), "+f"(d[34]), "+f"(d[35]), "+f"(d[36]), "+f"(d[37]), "+f"(d[38]), "+f"(d[39])
                 : "l"(da), "l"(db), "r"(acc));
}

constexpr int A1_THREADS = 384;
constexpr int A1_NST = 4;
#define A1_SKEW 8
constexpr int A1_STAGE = 16384 + WQ_STAGE;
constexpr int A1_KVP = 336;
constexpr int A1_SM_KV = 2 * A1_STAGE;
constexpr int A1_SM_END = A1_NST * A1_STAGE;
constexpr int A1_SM_BAR = A1_SM_END + 3072 + 3 * WOB + 64;
constexpr int A1_SM_RS = A1_SM_END + 512;
constexpr int A1_SM_W0 = A1_SM_END + 3072, A1_SM_W3 = A1_SM_END - 3 * WOB, A1_SM_A1 = 2 * WOB, A1_SM_A0 = A1_SM_A1 + 61440;
constexpr int A1_SM_XA = A1_SM_W0 + 2 * WOB, A1_SM_XB = A1_SM_XA + 2048;
constexpr int A1_SMEM = A1_SM_BAR + 512 + 7 * CST_EXTRA / 4;
static_assert(A1_SM_W3 >= A1_SM_KV + 144 * A1_KVP && A1_SM_W3 % 512 == 0 && A1_SM_A1 % 1024 == 0 && A1_SM_A0 <= A1_SM_KV && A1_SM_A0 + 61440 <= A1_SM_W3 && A1_SMEM <= 232448 && 11 * 4096 <= A1_STAGE, "layout");
__device__ __forceinline__ constexpr uint32_t wo_off(int h) { return h * WOB + (h < 3 ? A1_SM_W0 : h < 6 ? A1_SM_W3 - 3 * WOB : -6 * WOB); }
#define A1_FRED "red.relaxed.gpu.global.add.u32"
#define A1_FLD "ld.relaxed.gpu.global.u32"
#define ST_SLEEP 20
#define ST_SLEEP0 300
#define A1_P0 2
#define A1_PW (kb - 2)
#define A1_FSPIN SPIN_MAX
#define A1_FSLEEP 40
#define YT_LAYER 1
#define WOT 11
#define A1_P1 550
#define A1_P2 300
#define A1_WOAT 6

template <int L>
__device__ __forceinline__ void a1_mainloop(float (&acc)[120], uint32_t sbase, uint32_t bars, int wg, int tile) {
    constexpr int layer = L; (void)layer;
    const uint64_t da0 = L ? make_desc(sbase + wg * 8192, 8192, 1024, 1) : make_desc(sbase + wg * 8192, 16, 1024, 1), db0 = make_desc(sbase + 16384, 1024, 256, 3);
#pragma unroll 1
    for (int t = 0;; t++) {
        const int st = t % A1_NST;
        mbar_wait(bars + 8 * st, (t / A1_NST) & 1);
        if (t == A1_SKEW && wg == 0) mbar_wait(bars + 160, 0);
        TSTAMP3(1 + t);
        if (t == 0) CSA(0);
        wgmma_fence();
#pragma unroll
        for (int kk = 0; kk < 4; kk++) wgmma_n240<L, 1>(acc, da0 + (uint32_t)(st * (A1_STAGE / 16) + kk * (L ? 128 : 2)), db0 + (uint32_t)(st * (A1_STAGE / 16) + (kk >> 1) * (WQ_STAGE / 32) + (kk & 1) * 32), kk ? 1 : t);
        wgmma_commit();
        if (t == 9) break;
        if (t == A1_SKEW - 1 && wg == 0) wgmma_wait<0>(); else wgmma_wait<1>();
        if (t > 0 && (threadIdx.x & 127) == 0) {
            if (t != A1_SKEW || wg) mbar_arrive(bars + 8 * (A1_NST + (t - 1) % A1_NST));
            if (t == A1_SKEW - 1 && wg == 0) mbar_arrive(bars + 8 * (A1_NST + t % A1_NST));
        }
    }
}

template <bool MAP>
__global__ void __launch_bounds__(A1_THREADS, 1) a1_kernel(const __grid_constant__ Par in, const __grid_constant__ CUtensorMap tmX, const __grid_constant__ CUtensorMap tmR,
                                                           const __grid_constant__ CUtensorMap tmX1, const __grid_constant__ KgMaps tmW, const __grid_constant__ TileTab tab) {
#define layer in.layer
    const unsigned char* const wo = reinterpret_cast<const unsigned char*>(in.wop);
    float2* const rsum = reinterpret_cast<float2*>(in.sum);
    uint4* const of = in.of;
    extern __shared__ __align__(1024) unsigned char stg[];
    const uint32_t sbase = smem_u32(stg);
    const uint32_t bars = sbase + A1_SM_BAR;
    const uint32_t bar_stat = bars + 64, bar_kv = bars + 72, bar_rd = bars + 168;
    const uint32_t bar_wo = bars + 208, bar_done = bars + 216, bar_pv = bars + 224, bar_kvf = bars + 232, bar_f2 = bars + 248, bar_e2 = bars + 384, que = bars + 448;
    const int tid = threadIdx.x;
    CSK(0);
    const int w = __shfl_sync(~0u, tid >> 5, 0), wg = w >> 2;
    uint32_t smid;
    asm volatile("mov.u32 %0, %smid;" : "=r"(smid));
    const uint4 tv = tab.e[(MAP ? smid : blockIdx.x) + (tid & (smid >> 12))];
    const uint64_t pa = reinterpret_cast<const uint64_t*>(&in)[tid & (smid >> 12)], pb = reinterpret_cast<const uint64_t*>(&in)[6 + (tid & (smid >> 12))];
    const bool one = elect();
    uint32_t tz;
    const unsigned char* wq;
    auto entry = [&] { tz = __shfl_sync(~0u, tv.z, 0); wq = (const unsigned char*)(((uint64_t)__shfl_sync(~0u, tv.y, 0) << 32) | __shfl_sync(~0u, tv.x, 0)); };
    auto issue_w = [&](unsigned it) { bulk_load(sbase + (it % A1_NST) * A1_STAGE + 16384, wq + it * WQ_STAGE, WQ_STAGE, bars + 8 * (it % A1_NST)); };
    auto issue_x = [&](unsigned it, int kb) {
        asm volatile("cp.async.bulk.tensor.5d.shared::cluster.global.mbarrier::complete_tx::bytes [%0], [%1, {%3, %3, %3, %4, %5}], [%2];"
                     ::"r"(sbase + (it % A1_NST) * A1_STAGE), "l"(&tmX), "r"(bars + 8 * (it % A1_NST)), "r"(0), "r"(tz & 15), "r"(kb) : "memory");
    };
    auto first_x = [&] {
        issue_x(0, (tz >> 16) & 7); issue_x(1, ((tz >> 16) & 7) + 1);
    };
    auto expect = [&] {
#pragma unroll
        for (int i = 0; i < A1_NST; i++) mbar_expect_tx(bars + 8 * i, A1_STAGE);
    };
    if (w == 8) {
        if (one) {
            prefetch_tmap(&tmX); prefetch_tmap(&tmW.q);
#pragma unroll
            for (int i = 0; i < A1_NST; i++) mbar_init(bars + 8 * i, 1);
            asm volatile("fence.mbarrier_init.release.cluster;" ::: "memory");
        }
        __syncwarp();
        asm volatile("bar.arrive 0, 384;" ::: "memory");
        if (smid >> 12) __trap();
        entry();
        if ((tz & 0x80000010u) == 16) {
            if (one) {
                issue_w(0);
                asm volatile("griddepcontrol.wait;" ::: "memory");
                issue_x(0, (tz >> 16) & 7);
                expect();
                pause(A1_P1);
                issue_w(1);
                issue_x(1, ((tz >> 16) & 7) + 1);
                asm volatile("griddepcontrol.launch_dependents;" ::: "memory");
            }
#pragma unroll
            for (int kb = 2; kb < A1_NST; kb++) {
                __syncwarp();
                mbar_wait(bars + 8 * (kb - 2), 0);
                if (kb == 2) pause(A1_P2);
                if (one) { issue_x(kb, ((tz >> 16) & 7) + kb); issue_w(kb); }
                CSK(6 + kb);
            }
        }
        __syncwarp();
        if (!(tz & 16) && blockIdx.x < 128) kgen_first(in, tmW, sbase + A1_SM_W0, bars - 24, one);
        __syncwarp();
    }
    if (w > 8) CSK(8);
    const bool gen = w != 8 && in.logA && blockIdx.x < 128;
    KgPar kp;
    const int w11 = w < 8 ? 2 * (w & 3) + (w >> 2) : w - 1;
    if (gen) kgen_load(in, reinterpret_cast<const bf16*>(pa), w11, kp);
    if (w > 8) CSK(9);
    if (w == 8) {
        const int tile = tz >> 24, mb = tz & 15, hg = (tz >> 8) & 7, kb0 = (tz >> 16) & 7;
        const unsigned l1 = (tz >> 4) & 1;
        if (__builtin_expect(!l1, 0)) {
            CSK(1);
            const uint32_t ep = ld_epoch();
            if (one) {
                kgen_side(in, sbase + A1_SM_W0, bars - 24);
                if (tile < 128) { first_x(); expect(); }
                asm volatile("cp.async.bulk.wait_group 0;" ::: "memory");
            }
            __syncwarp();
            asm volatile("bar.arrive 10, 96;" ::: "memory");
            CSK(6);
            if (tile < 128) {
                await_all(96 + 32 * hg, ep * 15);
                if (one) issue_w(0);
                __syncwarp();
                mbar_wait(bars, 0);
                if (one) { issue_w(1); issue_x(2, kb0 + 2); issue_w(2); }
            }
            CSK(7);
            asm volatile("bar.sync 3, 384;" ::: "memory");
            if (tile < 128 && one) {
                fence_async_smem();
                issue_x(3, kb0 + 3); issue_w(3);
                mbar_expect_tx(bars + 240, 20480);
                bulk_load(sbase + A1_SM_W0, in.x + (size_t)(mb * 128 + hg * 16) * DM, 20480, bars + 240);
            }
            __syncwarp();
            CSK(9);
        } else asm volatile("bar.sync 3, 64;" ::: "memory");
        if (tile < 128 && elect()) {
#pragma unroll 1
            for (unsigned kb = A1_NST; kb < 10; kb++) {
                mbar_wait(bars + 8 * (A1_NST + kb % A1_NST), ((kb / A1_NST) - 1) & 1);
                if (l1 && kb < 9) mbar_wait(bar_rd + 8 * (kb - A1_NST), 0);
                mbar_expect_tx(bars + 8 * (kb % A1_NST), A1_STAGE);
                issue_x(kb, kb < 5 ? kb + kb0 : kb - kb0); issue_w(kb);
                if (kb == (l1 ? A1_WOAT : 9)) {
                    if (!l1) { mbar_wait(bar_stat, 0); asm volatile("fence.proxy.async.global;" ::: "memory"); }
                    mbar_expect_tx(bar_wo, 8 * WOB);
                    bulk_load(sbase + A1_SM_W0, wo + hg * 8 * WOB, 2 * WOB, bar_wo);
                }
            }
            mbar_wait(bars + 8 * (A1_NST + 3), 1);
            bulk_load(sbase + A1_SM_W3, wo + (hg * 8 + 3) * WOB, 3 * WOB, bar_wo);
        }
        CSA(4); CSA_END;
        return;
    }
    {
        if (w < 8 && one) {
#pragma unroll 1
            for (uint32_t c = (w & 4 ? w & 2 ? 0x1111112'01111111ull : 0x1111111'01111184ull : w & 2 ? 0x3122222'01111111ull : 0x1111132'02220000ull) >> (32 * (w & 1)), b = bars + 56 * w; c; c >>= 4, b += 8)
                if (c & 15) mbar_init(b, c & 15);
            asm volatile("fence.mbarrier_init.release.cluster;" ::: "memory");
        }
        __syncwarp();
        asm volatile("bar.sync 0, 384;" ::: "memory");
        if (layer) {
            if (w == 9) asm volatile("bar.arrive 3, 64;" ::: "memory");
        } else {
            if (gen) { SPAN(0, 0); SPAN(0, 1); kgen_tables(in, reinterpret_cast<uint4*>(stg + 3 * A1_STAGE), w11, kp); }
            else if (w != 11 && w11 > 1) asm volatile("bar.arrive 9, 352;" ::: "memory");
            __syncwarp();
            if (w11 < 2) {
                asm volatile("bar.sync 10, 96;" ::: "memory");
                kgen_sums(in, sbase + A1_SM_W0, w11);
                __syncwarp();
                asm volatile("bar.arrive 9, 352;" ::: "memory");
                CSK(1);
            }
            if (w == 9) asm volatile("bar.sync 3, 384;" ::: "memory"); else asm volatile("bar.arrive 3, 384;" ::: "memory");
        }
    }
    tz = __shfl_sync(~0u, tv.z + (uint32_t)(pb >> 32), 0);
    const int tile = tz >> 24, mb = tz & 15, hg = (tz >> 8) & 7;
    float2* rst = reinterpret_cast<float2*>(stg + A1_SM_RS) + 8;
    if (wg == 2) {
        if (w == 11 && layer == 0) {
            asm volatile("bar.sync 9, 352;" ::: "memory");
            CSK(5);
            if (one) publish(64);
            __syncwarp();
            CSK(6);
        }
        if (tile >= 128) { sm_idle(layer); return; }
        if (w == 10) {
            if (one) { prefetch_tmap(&tmR); prefetch_tmap(&tmX1); }
            uint32_t ns;
            asm volatile("mov.u32 %0, %nsmid;" : "=r"(ns));
            if (MAP && ns != 132) __trap();
        }
        __syncwarp();
        if (w == 9) {
            if (layer && one) {
                mbar_expect_tx(bar_stat, 3840);
                bulk_load(sbase + A1_SM_XB, g_xb + tile * 240, 3840, bar_stat);
            }
            __syncwarp();
#pragma unroll 1
            for (int it = 0; it < 4096 * layer; it++) {
                uint32_t ok;
                asm volatile("{\n.reg .pred p;\nmbarrier.try_wait.parity.shared::cta.b64 p, [%1], %2;\nselp.b32 %0, 1, 0, p;\n}" : "=r"(ok) : "r"(bars + 8), "n"(0) : "memory");
                if (__any_sync(~0u, ok)) break;
            }
            uint4* pre = of + (mb * 8 + hg) * 1280 + (tid - 288);
#pragma unroll 1
            for (int k = 0; k < 5 + 5 * layer; k++) {
#pragma unroll
                for (int i = 0; i < 8; i++) asm volatile("st.global.v4.u32 [%0], {%1,%1,%1,%1};" ::"l"(pre + 32 * i), "r"(~0u) : "memory");
                pre += k < 5 ? 256 : XCP / 8;
                if (layer) pause(400);
                if (k == 4) {
                    CSA(2);
                    asm volatile("fence.acq_rel.gpu;" ::: "memory");
                    asm volatile("fence.proxy.async.global;" ::: "memory");
                    __syncwarp();
                    if (tid == 288) mbar_arrive(bar_done);
                    CSA(3);
                    pre = reinterpret_cast<uint4*>(g_yT) + tile * (5 * XCP / 8) + (tid - 288);
                }
            }
            if (layer == 0) {
                asm volatile("griddepcontrol.launch_dependents;" ::: "memory");
                await_all(64, ld_epoch() * gridDim.x);
                CSA(5);
                float4 a[2] = {};
#pragma unroll
                for (int k = 0; k < 10; k++)
#pragma unroll
                    for (int h = 0; h < 2; h++) {
                        const int c4 = min(tid - 288 + 32 * h, 59);
                        const float4 v = __ldcg(reinterpret_cast<const float4*>(g_csp + (k / 5) * 9600 + (k % 5) * 640 + hg * 80) + c4 + (c4 / 20) * 780);
                        a[h].x += v.x; a[h].y += v.y; a[h].z += v.z; a[h].w += v.w;
                    }
#pragma unroll
                for (int h = 0; h < 2; h++)
#pragma unroll
                    for (int k = 0; k < 4; k++) {
                        const float c = 0.5f * (k == 0 ? a[h].x : k == 1 ? a[h].y : k == 2 ? a[h].z : a[h].w), c1 = c - rbf(c), c2 = c1 - rbf(c1);
                        *reinterpret_cast<uint4*>(stg + A1_SM_XB + (4 * min(tid - 288 + 32 * h, 59) + k) * 16) = make_uint4(pack2(c, c1), pack2(c2, 0.f), 0u, 0u);
                    }
                fence_async_smem();
                __syncwarp();
                if (one) {
                    bulk_store(g_xb + tile * 240, sbase + A1_SM_XB, 3840);
                    asm volatile("cp.async.bulk.commit_group;" ::: "memory");
                    asm volatile("cp.async.bulk.wait_group.read 0;" ::: "memory");
                    mbar_arrive(bar_stat);
                }
                __syncwarp();
                CSA(1);
            }
            TSTAMP1T(9, 288);
        } else {
            const int j = tid - 320;
            const uint32_t tag = ld_epoch();
            if (tid == 352) sm_started(layer);
            const int ch = j & 7, kg = (j >> 3) & 3;
            const unsigned char* src = stg + (layer ? (j >> 5) * 8192 + (hg & 3) * 2048 : A1_SM_W0 + (j >> 2) * 1280);
            const int of0 = layer ? kg * 128 + ((ch ^ kg) << 4) : (j & 7) << 4, ofx = layer ? 576 : 64, ofy = layer ? 1024 : 128;
            float s[8], q[8], p0[8];
#pragma unroll
            for (int i = 0; i < 8; i++) { s[i] = 0.f; q[i] = 0.f; }
#pragma unroll 1
            for (int it = 0; it < 5; it++) {
                uint4 v[4];
                mbar_wait(layer ? bars + 8 * (it % A1_NST) : bars + 240, layer * it / A1_NST);
#pragma unroll
                for (int k = 0; k < 4; k++) v[k] = *reinterpret_cast<const uint4*>(src + (layer ? (it % A1_NST) * A1_STAGE : it * 256) + (k & 1 ? of0 ^ ofx : of0) + (k >> 1) * ofy);
                if (it == 0) {
                    const uint4 pv = *reinterpret_cast<const uint4*>(src + (layer ? ch << 4 : 0));
                    const uint32_t w[4] = {pv.x, pv.y, pv.z, pv.w};
#pragma unroll
                    for (int i = 0; i < 4; i++) { p0[2 * i] = __uint_as_float((layer ? w[i] : w[0]) << 16); p0[2 * i + 1] = __uint_as_float(layer ? w[i] & 0xffff0000u : w[0] << 16); }
                }
                asm volatile("" :: "r"(v[0].x), "r"(v[1].x), "r"(v[2].x), "r"(v[3].x), "f"(p0[0]) : "memory");
                __syncwarp();
                if ((tid & 31) == 0) mbar_arrive(bar_rd + 8 * it);
#pragma unroll
                for (int k = 0; k < 4; k++) {
                    const uint32_t w[4] = {v[k].x, v[k].y, v[k].z, v[k].w};
#pragma unroll
                    for (int i = 0; i < 4; i++) {
                        const float a = __uint_as_float(w[i] << 16) - p0[2 * i], b = __uint_as_float(w[i] & 0xffff0000u) - p0[2 * i + 1];
                        s[2 * i] += a; s[2 * i + 1] += b; q[2 * i] = fmaf(a, a, q[2 * i]); q[2 * i + 1] = fmaf(b, b, q[2 * i + 1]);
                    }
                }
            }
            float o[4];
            int row;
            if (layer == 0) {
                float s0 = ((s[0] + s[1]) + (s[2] + s[3])) + ((s[4] + s[5]) + (s[6] + s[7])), q0 = ((q[0] + q[1]) + (q[2] + q[3])) + ((q[4] + q[5]) + (q[6] + q[7]));
#pragma unroll
                for (int o = 1; o <= 2; o <<= 1) { s0 += __shfl_xor_sync(~0u, s0, o); q0 += __shfl_xor_sync(~0u, q0, o); }
                if ((j & 3) == 0) {
                    const float d = s0 * (1.0f / DM);
                    const uint32_t ms = pack2(p0[0] + d, sqrt_apx(rbf(rbf(fmaxf(fmaf(-d, d, q0 * (1.0f / DM)), 0.f)) + 1e-5f)));
                    asm volatile("st.global.cg.u64 [%0], %1;" ::"l"(g_rstat + mb * 128 + (j & 4) * 16 + hg * 8 + (j >> 3)), "l"(tagw(ms, tag)) : "memory");
                    g_piv[mb * 128 + hg * 16 + ((j >> 2) & 8) + (j & 4) + ((j >> 3) & 3)] = __ushort_as_bfloat16((unsigned short)ms);
                }
                ulonglong2 v;
#pragma unroll 1
                for (int it = 0; it < SPIN_MAX; it++) {
                    v = ld_tag2(reinterpret_cast<const ulonglong2*>(g_rstat + mb * 128) + j);
                    if (__all_sync(~0u, tag_ok(v, tag))) break;
                    __nanosleep(100);
                }
                o[0] = __uint_as_float((uint32_t)v.x << 16); o[1] = rcp_apx(__uint_as_float((uint32_t)v.x & 0xffff0000u));
                o[2] = __uint_as_float((uint32_t)v.y << 16); o[3] = rcp_apx(__uint_as_float((uint32_t)v.y & 0xffff0000u));
                row = 2 * j;
            } else {
#pragma unroll
                for (int i = 0; i < 4; i++) {
                    const bool up = kg & 2;
                    const float ss = __shfl_xor_sync(~0u, up ? s[i] : s[i + 4], 16), qq = __shfl_xor_sync(~0u, up ? q[i] : q[i + 4], 16);
                    s[i] = (up ? s[i + 4] : s[i]) + ss; q[i] = (up ? q[i + 4] : q[i]) + qq; p0[i] = up ? p0[i + 4] : p0[i];
                }
#pragma unroll
                for (int i = 0; i < 2; i++) {
                    const bool up = kg & 1;
                    const float ss = __shfl_xor_sync(~0u, up ? s[i] : s[i + 2], 8), qq = __shfl_xor_sync(~0u, up ? q[i] : q[i + 2], 8);
                    s[i] = (up ? s[i + 2] : s[i]) + ss; q[i] = (up ? q[i + 2] : q[i]) + qq; p0[i] = up ? p0[i + 2] : p0[i];
                }
                uint4* gp = g_halo + 86016 + mb * 512 + j;
                const float d0 = s[0] * (1.0f / 80.0f), d1 = s[1] * (1.0f / 80.0f);
                asm volatile("st.relaxed.gpu.global.v4.f32 [%0], {%1,%2,%3,%4};" ::"l"(gp + hg * 64), "f"(p0[0] + d0), "f"(fmaxf(fmaf(-d0, s[0], q[0]), 0.f)), "f"(p0[1] + d1), "f"(fmaxf(fmaf(-d1, s[1], q[1]), 0.f)) : "memory");
                __nanosleep(ST_SLEEP0);
                uint32_t pw[8][4], todo = 0xff;
#pragma unroll 1
                for (int it = 0; it < SPIN_MAX; it++) {
#pragma unroll
                    for (int k = 0; k < 8; k++)
                        if (todo >> k & 1) asm volatile("ld.relaxed.gpu.global.v4.u32 {%0,%1,%2,%3}, [%4];" : "=r"(pw[k][0]), "=r"(pw[k][1]), "=r"(pw[k][2]), "=r"(pw[k][3]) : "l"(gp + k * 64) : "memory");
#pragma unroll
                    for (int k = 0; k < 8; k++)
                        if (__all_sync(~0u, pw[k][0] != ~0u && pw[k][1] != ~0u && pw[k][2] != ~0u && pw[k][3] != ~0u)) todo &= ~(1u << k);
                    if (!todo) break;
                    __nanosleep(ST_SLEEP);
                }
#pragma unroll
                for (int r = 0; r < 2; r++) {
                    float mean = 0.f, m2 = 0.f;
#pragma unroll
                    for (int k = 0; k < 8; k++) mean += __uint_as_float(pw[k][2 * r]);
                    mean *= 0.125f;
#pragma unroll
                    for (int k = 0; k < 8; k++) {
                        const float dm = __uint_as_float(pw[k][2 * r]) - mean;
                        m2 += fmaf(80.0f * dm, dm, __uint_as_float(pw[k][2 * r + 1]));
                    }
                    o[2 * r] = rbf(mean);
                    o[2 * r + 1] = rcp_apx(rbf(sqrt_apx(rbf(rbf(m2 * (1.0f / DM)) + 1e-5f))));
                }
                row = (j >> 5) * 64 + (j & 7) * 8 + ((j >> 3) & 3) * 2;
                if (hg == 0) *reinterpret_cast<uint32_t*>(g_piv + SEQ + mb * 128 + 2 * (row & 60) + 4 * (row >> 6) + (row & 3)) = __byte_perm(__float_as_uint(o[0]), __float_as_uint(o[2]), 0x7632);
            }
#pragma unroll
            for (int r = 0; r < 2; r++)
                *reinterpret_cast<uint4*>(stg + A1_SM_XA + (row + r) * 16) = make_uint4(__byte_perm(__float_as_uint(-o[2 * r]), 0, 0x3232), __float_as_uint(-o[2 * r]) >> 16, 0u, 0u);
            *reinterpret_cast<float4*>(rst + row + (row >> 6) * 8) = make_float4(o[0], o[1], o[2], o[3]);
            fence_async_smem();
            TSTAMP1T(7, 320); CSA(1);
            if (tid == 320) DBGC(44);
            __syncwarp();
            if ((tid & 31) == 0) mbar_arrive(bar_stat);
        }
        CSA(4); CSA_END;
        if (tid == 320) DBGCAL(0);
        __syncwarp();
        if (w == WOT) {
            mbar_wait(bars + 416, 0);
            mbar_wait(bar_done, 0);
            if (one) {
                bulk_load(sbase, wo + (hg * 8 + 6) * WOB, 2 * WOB, bar_wo);
                bulk_load(sbase + A1_SM_W0 + 2 * WOB, wo + (hg * 8 + 2) * WOB, WOB, bar_wo);
            }
            __syncwarp();
        }
#define FWA 11
#define FWB 10
        if (w == FWA || w == FWB) {
            const int cw = w == FWB;
            const uint32_t* fl = reinterpret_cast<const uint32_t*>(rsum + 2 * SEQ) + (((layer * 16 + mb) * 2 + cw) * 8 + (tid & 7)) * FSTR;
            const unsigned char* src = reinterpret_cast<const unsigned char*>(of) + mb * 163840 + cw * 10240 + (tid & 7) * 20480;
            const uint32_t sl = sbase + (cw ? A1_SM_A1 : A1_SM_A0);
            mbar_wait(cw ? bar_done : bar_kvf, 0);
            if (one) {
                mbar_expect_tx(bar_f2 + 64 * cw + 64, 10240);
                tma_load_3d(sl + 51200, &tmR, layer ? 0 : hg * 80, layer ? hg * 80 : mb * 64, layer ? mb * 2 + cw : cw, bar_f2 + 64 * cw + 64);
            }
            __syncwarp();
            uint32_t pend = 0xffu & ~(1u << hg), v = 0;
            const uint32_t bo = wo_off((tid & 7) + ((tid & 7) < hg)) >> 4, lt = (1u << (tid & 31)) - 1;
#pragma unroll 1
            for (int it = 0; pend && it < 2 * SPIN_MAX; it++) {
                if (v != 4 && (pend >> (tid & 31) & 1)) asm volatile(A1_FLD " %0, [%1];" : "=r"(v) : "l"(fl) : "memory");
                uint32_t fr;
                asm volatile("{\n.reg .pred p;\nmbarrier.test_wait.parity.shared::cta.b64 p, [%1], 0;\nselp.b32 %0, 1, 0, p;\n}" : "=r"(fr) : "r"(bar_e2 + 16 * cw + (tid & 1) * 8) : "memory");
                fr = __ballot_sync(~0u, fr);
                uint32_t m = __ballot_sync(~0u, v == 4 || it >= A1_FSPIN) & pend;
                const int q = 8 - __popc(pend) + __popc(m & lt);
                m &= __ballot_sync(~0u, q < ((fr & 2) ? 8 : (fr & 1) ? 7 : 5));
                pend ^= m;
                if (m >> (tid & 31) & 1) DBGC(12 + cw * 8 + (tid & 7));
                if (!m) __nanosleep(A1_FSLEEP);
                if (m >> (tid & 31) & 1) {
                    bulk_load(q == 7 && !cw ? sbase + A1_SM_W0 : sl + (q < 6 ? q : q - 6) * 10240, src, 10240, bar_f2 + 64 * cw + 8 * q);
                    asm volatile("st.shared.u32 [%0], %1;" ::"r"(que + 32 * cw + 4 * q), "r"(bo) : "memory");
                    mbar_expect_tx(bar_f2 + 64 * cw + 8 * q, 10240);
                    DBGC(44 + cw * 8 + q);
                }
                __syncwarp();
            }
        }
    } else if (tile < 128) {
        SPAN(1 + 4 * layer, 0);
        constexpr int on = 1;
        float acc[120];
        const int lane = tid & 31, warp = w & 7, g = lane >> 2, t = lane & 3;
        if (on) {
            SPAN(1 + 4 * layer, 1);
            TSTAMP1(0);
            if (threadIdx.x == 0) { GSTAMP(g_tim1, 15); }
            TSTAMP3(0);
            if (tid == 0) TSTAMP2(0);
            TSTAMP4(0);
            if (tid == 0) DBGC(60);
            if (layer == 0) a1_mainloop<0>(acc, sbase, bars, wg, tile); else a1_mainloop<1>(acc, sbase, bars, wg, tile);
            uint32_t ok;
            asm volatile("{\n.reg .pred p;\nmbarrier.test_wait.parity.shared::cta.b64 p, [%1], 0;\nselp.b32 %0, 1, 0, p;\n}" : "=r"(ok) : "r"(bar_stat) : "memory");
            if (tid == 128 && !ok) mbar_arrive(bars + 160);
            __syncwarp();
            mbar_wait(bar_stat, 0);
            wgmma_fence();
            wgmma_n240<0, 0>(acc, make_desc(sbase + A1_SM_XA + wg * 1024, 0, 128, 0), make_desc(sbase + A1_SM_XB, 0, 128, 0), 1);
            wgmma_commit();
            if (tid == 128 && ok) mbar_arrive(bars + 160);
            mbar_wait(bars + 8 * (A1_NST + 3), 1);
        }
        uint4* hp = g_halo + (((layer * 16 + mb - ((warp & 3) != 3)) * 8 + hg) * 2 + wg) * 168 + lane;
        float* hr = reinterpret_cast<float*>(hp - lane + 160) + ((warp & 3) == 3 ? g : 2 * t);
        asm volatile("" : "+l"(hp), "+l"(hr));
        const float2* rw = rst + 16 * warp + 8 * wg;
        const float rb0 = rw[g + 8].y, ra = rw[g].y * 0.22360679774997896f, rb = rb0 * 0.22360679774997896f;
        wgmma_wait<0>();
        if ((tid & 127) == 0) mbar_arrive(bar_done);
        TSTAMP1(2); CSA(1);
        TSTAMP1T(13, 224);
        if ((tid & 127) == 0) DBGC(62 - wg);
        uint32_t f[2][30];
#pragma unroll
        for (int j = 10; j < 30; j++) f[1][j] = pack2(acc[4 * j + 2], acc[4 * j + 3]);
        if ((warp & 3) == 3) {
#pragma unroll
            for (int j = 0; j < 20; j += 4) {
                const int a = j < 12 ? 10 + j : 8 + j, b = j == 8 ? 28 : a + 2;
                asm volatile("st.relaxed.gpu.global.v4.u32 [%0], {%1,%2,%3,%4};" ::"l"(hp + 8 * j), "r"(f[1][a]), "r"(f[1][a + 1]), "r"(f[1][b]), "r"(f[1][b + 1]) : "memory");
            }
            if (t == 0) asm volatile("st.relaxed.gpu.global.f32 [%0], %1;" ::"l"(hr), "f"(rb0) : "memory");
        }
        TSTAMP1T(12, 224);
        const uint32_t kvw = sbase + A1_SM_KV + (16 * warp + 8 * wg) * A1_KVP;
        const uint32_t mrow = kvw + (lane & 7) * A1_KVP + (lane >> 3) * 16;
#pragma unroll
        for (int j = 0; j < 20; j += 4) {
            const int a = j < 12 ? 10 + j : 8 + j, b = j == 8 ? 28 : a + 2;
            stsm_x4(mrow + 16 * A1_KVP + 16 * (a - 10) + (j == 8 ? (lane & 16) * 8 : 0), f[1][a], f[1][a + 1], f[1][b], f[1][b + 1]);
        }
        __syncwarp();
        if (lane == 0 && (warp & 3) != 3) mbar_arrive(bar_kv + 8 * (warp + 1));
#pragma unroll
        for (int j = 0; j < 30; j++) f[0][j] = pack2(acc[4 * j], acc[4 * j + 1]);
        stsm_x4(mrow + 8 * A1_KVP + 160, f[0][20], f[0][21], f[0][22], f[0][23]);
        stsm_x4(mrow + 8 * A1_KVP + 224, f[0][24], f[0][25], f[0][26], f[0][27]);
        asm volatile("stmatrix.sync.aligned.m8n8.x2.shared.b16 [%0], {%1,%2};" ::"r"(mrow + 8 * A1_KVP + 288), "r"(f[0][28]), "r"(f[0][29]) : "memory");
#pragma unroll
        for (int j = 0; j < 10; j++) f[1][j] = pack2(acc[4 * j + 2], acc[4 * j + 3]);
        __syncwarp();
        uint32_t vb[10][2], hv[24] = {}, *kp = hv, *vp = hv + 12;
#pragma unroll
        for (int j = 0; j < 10; j += 2) ldsm_x4_t(&vb[j][0], kvw + (8 + (lane & 15)) * A1_KVP + 160 + (lane >> 4) * 16 + 16 * j);
        const bool up0 = 2 * t > g, up1 = 2 * t + 1 > g, edge = (mb | (warp & 3)) == 0;
        float rk[4];
        auto above = [&]() {
            mbar_wait(bar_kv + 8 * warp, 0);
#pragma unroll
            for (int j = 0; j < 12; j += 4) ldsm_x4(&kp[j], mrow + 16 * j);
            rk[0] = rw[2 * t - (up0 ? 8 : 0)].y; rk[1] = rw[2 * t + 1 - (up1 ? 8 : 0)].y;
#pragma unroll
            for (int j = 0; j < 8; j += 4) ldsm_x4_t(&vp[j], mrow + 160 + 16 * j);
            asm volatile("ldmatrix.sync.aligned.m8n8.x2.trans.shared.b16 {%0,%1}, [%2];" : "=r"(vp[8]), "=r"(vp[9]) : "r"(mrow + 288) : "memory");
            __syncwarp();
            if (lane == 0) mbar_arrive(bar_kvf);
        };
        auto ask = [&]() {
            if (mb > 0) {
#pragma unroll
                for (int k = 0; k < 20; k += 4)
                    asm volatile("ld.relaxed.gpu.global.v4.u32 {%0,%1,%2,%3}, [%4];" : "=r"(hv[k]), "=r"(hv[k + 1]), "=r"(hv[k + 2]), "=r"(hv[k + 3]) : "l"(hp + 8 * k) : "memory");
                asm volatile("ld.relaxed.gpu.global.v2.u32 {%0,%1}, [%2];" : "=r"(hv[20]), "=r"(hv[21]) : "l"(hr) : "memory");
            }
        };
        auto halo = [&]() {
            if (lane == 0) mbar_arrive(bar_kvf);
            rk[0] = rw[2 * t].y; rk[1] = rw[2 * t + 1].y;
#pragma unroll 1
            for (int it = 0; it < SPIN_MAX; it++) {
                uint32_t m = max(hv[20], hv[21]);
#pragma unroll
                for (int k = 0; k < 20; k += 2) m = __vimax3_u32(m, hv[k], hv[k + 1]);
                if (!__any_sync(~0u, m == ~0u)) break;
                ask();
            }
            if (wg && lane == 0) mbar_arrive(bars + 416);
            if (up0) rk[0] = __uint_as_float(hv[20]);
            if (up1) rk[1] = __uint_as_float(hv[21]);
#pragma unroll
            for (int j = 0; j < 10; j++) asm volatile("movmatrix.sync.aligned.m8n8.trans.b16 %0, %1;" : "=r"(vp[j]) : "r"(hv[j < 8 ? 12 + j : 2 + j]));
        };
        rk[2] = rw[2 * t + (up0 ? 0 : 8)].y; rk[3] = rw[2 * t + 1 + (up1 ? 0 : 8)].y;
        uint32_t qs[4][2];
#pragma unroll
        for (int h = 0; h < 4; h++) {
            qs[h][0] = (t >> 1) == (h & 1) ? f[0][5 * (h >> 1) + 2] : 0u; qs[h][1] = (t >> 1) == (h & 1) ? f[1][5 * (h >> 1) + 2] : 0u;
            asm volatile("" : "+r"(qs[h][0]), "+r"(qs[h][1]));
        }
#pragma unroll
        for (int j = 0; j < 10; j++) asm volatile("" : "+r"(f[0][j]), "+r"(f[1][j]), "+r"(f[0][10 + j]));
        if (warp & 3) above(); else if (wg) ask(); else hv[20] = mb ? ~0u : 0u;
        TSTAMP1T(10, 64); CSA(2);
        if (warp && !wg) mbar_wait(bars + 416 + 8 * warp, 0);
        CSA(3);
        float sc[4][3][4];
#pragma unroll
        for (int h = 0; h < 4; h++) {
            const int jb = 5 * (h >> 1) + 3 * (h & 1), js = 5 * (h >> 1) + 2;
#pragma unroll
            for (int nt = 1; nt < 3; nt++) {
#pragma unroll
                for (int e = 0; e < 4; e++) sc[h][nt][e] = 0.f;
                mma_bf16(sc[h][nt], f[0][jb], f[1][jb], f[0][jb + 1], f[1][jb + 1], f[nt - 1][10 + jb], f[nt - 1][11 + jb]);
                mma_bf16_k8(sc[h][nt], qs[h][0], qs[h][1], f[nt - 1][10 + js]);
            }
        }
        if (!(warp & 3)) halo();
        TSTAMP1(8); CSA(4);
#pragma unroll
        for (int h = 0; h < 4; h++) {
            const int jb = 5 * (h >> 1) + 3 * (h & 1), js = 5 * (h >> 1) + 2;
#pragma unroll
            for (int e = 0; e < 4; e++) sc[h][0][e] = 0.f;
            mma_bf16(sc[h][0], f[0][jb], f[1][jb], f[0][jb + 1], f[1][jb + 1], kp[jb], kp[jb + 1]);
            mma_bf16_k8(sc[h][0], qs[h][0], qs[h][1], kp[js]);
        }
        TSTAMP1T(3, 64);
        float p[4][4], sum[4][2];
        uint32_t lg[4][2], mx[4];
        const float rl[4] = {rk[0] * ra, rk[1] * ra, rk[2] * rb, rk[3] * rb};
        auto max2 = [](uint32_t a, uint32_t b) { uint32_t r; asm("max.bf16x2 %0, %1, %2;" : "=r"(r) : "r"(a), "r"(b)); return r; };
#pragma unroll
        for (int h = 0; h < 4; h++) {
            lg[h][0] = pack2((up0 ? sc[h][0][0] : sc[h][1][0]) * rl[0], (up0 ? sc[h][1][2] : sc[h][2][2]) * rl[2]);
            lg[h][1] = pack2((up1 ? sc[h][0][1] : sc[h][1][1]) * rl[1], (up1 ? sc[h][1][3] : sc[h][2][3]) * rl[3]);
            if (edge) {
                if (up0) lg[h][0] = __byte_perm(lg[h][0], 0xce6eu, 0x3254);
                if (up1) lg[h][1] = __byte_perm(lg[h][1], 0xce6eu, 0x3254);
            }
            mx[h] = max2(lg[h][0], lg[h][1]);
        }
#pragma unroll
        for (int o = 1; o <= 2; o <<= 1)
#pragma unroll
            for (int h = 0; h < 4; h++) mx[h] = max2(mx[h], __shfl_xor_sync(~0u, mx[h], o));
#pragma unroll
        for (int h = 0; h < 4; h++)
#pragma unroll
            for (int r = 0; r < 2; r++) {
                const float m = __uint_as_float(r ? mx[h] & 0xffff0000u : mx[h] << 16);
#pragma unroll
                for (int e = 0; e < 2; e++)
                    asm("ex2.approx.ftz.f32 %0, %1;" : "=f"(p[h][2 * r + e]) : "f"((__uint_as_float(r ? lg[h][e] & 0xffff0000u : lg[h][e] << 16) - m) * 1.4426950408889634f));
            }
#pragma unroll
        for (int h = 0; h < 4; h++) {
            float d0, d1;
            asm("{\n.reg .b32 a, b;\ncvt.rn.f16x2.f32 a, %5, %4;\ncvt.rn.f16x2.f32 b, %7, %6;\n"
                "mma.sync.aligned.m16n8k8.row.col.f32.f16.f16.f32 {%0,%1,%2,%3}, {a,b}, {%8}, {%9,%9,%9,%9};\n}"
                : "=f"(sum[h][0]), "=f"(d0), "=f"(sum[h][1]), "=f"(d1) : "f"(p[h][0]), "f"(p[h][1]), "f"(p[h][2]), "f"(p[h][3]), "r"(0x3c003c00u), "f"(0.f));
        }
        TSTAMP1T(5, 64); CSA(5);
        const uint32_t mu = (up0 ? 0xffffu : 0u) | (up1 ? 0xffff0000u : 0u);
        uint32_t ob[10][2];
#pragma unroll
        for (int P = 0; P < 2; P++) {
            float os[2][4];
#pragma unroll
            for (int e = 0; e < 2; e++) {
                const int h = 2 * P + e;
                const float i0 = rcp_apx(sum[h][0]), i1 = rcp_apx(sum[h][1]);
                const uint32_t w0 = pack2(p[h][0] * rk[0] * i0, p[h][1] * rk[1] * i0), w1 = pack2(p[h][2] * rk[2] * i1, p[h][3] * rk[3] * i1);
#pragma unroll
                for (int dt = 0; dt < 3; dt++) {
                    const int j = 5 * P + (dt < 2 ? 3 * e + dt : 2);
                    float o[4] = {0.f, 0.f, 0.f, 0.f};
                    mma_bf16(o, w0 & ~mu, w1 & mu, 0u, w1 & ~mu, vb[j][0], vb[j][1]);
                    mma_bf16_k8(o, w0 & mu, 0u, vp[j]);
                    if (dt < 2) { ob[j][0] = pack2(o[0], o[1]); ob[j][1] = pack2(o[2], o[3]); }
                    else { os[e][0] = o[0]; os[e][1] = o[1]; os[e][2] = o[2]; os[e][3] = o[3]; }
                }
            }
#pragma unroll
            for (int k = 0; k < 4; k++) os[0][k] = t < 2 ? os[0][k] : os[1][k];
            ob[5 * P + 2][0] = pack2(os[0][0], os[0][1]); ob[5 * P + 2][1] = pack2(os[0][2], os[0][3]);
        }
        const uint32_t sl = sbase + (wg ? A1_SM_A1 : A1_SM_A0);
        const uint32_t o0 = (warp & 3) * 2048 + g * 64 + ((t ^ (g >> 1)) << 4), o1 = 8192 + (warp & 3) * 512 + g * 32 + ((t ^ ((g >> 2) << 1)) << 3);
        CSA(15);
#pragma unroll
        for (int j = 0; j < 10; j++) asm volatile("" : "+r"(ob[j][0]), "+r"(ob[j][1]) :: "memory");
        if (wg == 0 && lane == 0) mbar_arrive(bar_pv);
        mbar_wait(bar_done, 0);
        if (wg == 0) mbar_wait(bar_kvf, 0);
#pragma unroll
        for (int h = 0; h < 2; h++) {
            asm volatile("st.shared.v4.u32 [%0], {%1,%2,%3,%4};" ::"r"(sl + o0 + h * 1024), "r"(ob[0][h]), "r"(ob[1][h]), "r"(ob[2][h]), "r"(ob[3][h]) : "memory");
            asm volatile("st.shared.v4.u32 [%0], {%1,%2,%3,%4};" ::"r"(sl + o0 + h * 1024 + 512), "r"(ob[4][h]), "r"(ob[5][h]), "r"(ob[6][h]), "r"(ob[7][h]) : "memory");
            asm volatile("st.shared.v2.u32 [%0], {%1,%2};" ::"r"(sl + o1 + h * 256), "r"(ob[8][h]), "r"(ob[9][h]) : "memory");
        }
        if (warp > 4 && lane == 0) mbar_arrive(bars + 384 + 8 * warp);
        fence_async_smem();
        __syncwarp();
        TSTAMP1T(4, 64); CSA(6);
        TSTAMP1(1);
        TSTAMP2(1);
        const unsigned char* ot = reinterpret_cast<const unsigned char*>(of) + mb * 163840 + wg * 10240;
        if (lane == 0) {
            asm volatile("cp.async.bulk.global.shared::cta.bulk_group [%0], [%1], 2048;" ::"l"(ot + hg * 20480 + (warp & 3) * 2048), "r"(sl + (warp & 3) * 2048) : "memory");
            asm volatile("cp.async.bulk.global.shared::cta.bulk_group [%0], [%1], 512;" ::"l"(ot + hg * 20480 + 8192 + (warp & 3) * 512), "r"(sl + 8192 + (warp & 3) * 512) : "memory");
            asm volatile("cp.async.bulk.commit_group;" ::: "memory");
            asm volatile("cp.async.bulk.wait_group 0;" ::: "memory");
            asm volatile(A1_FRED " [%0], 1;" ::"l"(reinterpret_cast<uint32_t*>(rsum + 2 * SEQ) + (((layer * 16 + mb) * 2 + wg) * 8 + hg) * FSTR) : "memory");
            DBGC(4 + warp);
        }
        TSTAMP4(11); CSA(7);
        float ac2[40];
        const uint64_t db0 = make_desc(sbase, 1024, 256, 3), db1 = make_desc(sbase + 10240, 512, 256, 3), da0 = make_desc(sl, 16, 1024, 2), da1 = make_desc(sl + 8192, 16, 256, 3);
        const uint32_t o7 = wg ? 640 : (A1_SM_W0 - A1_SM_A0) >> 4;
        const uint32_t trow = ((lane & 7) + 8 * (lane >> 4)) * 128 + (((2 * (warp & 3) + ((lane >> 3) & 1)) ^ (lane & 7)) << 4);
        uint32_t xr[10][2];
        mbar_wait(bar_f2 + 64 * wg + 64, 0);
        if (layer == 0) {
#pragma unroll
            for (int j = 0; j < 10; j += 2) ldsm_x4(&xr[j][0], sl + 51200 + (16 * (warp & 3) + (lane & 15)) * 160 + (lane >> 4) * 16 + 16 * j);
        } else {
#pragma unroll
            for (int j = 0; j < 10; j += 2) ldsm_x4_t(&xr[j][0], sl + 51200 + trow + 1024 * j);
        }
        const uint32_t ri = __shfl_sync(~0u, layer * SEQ + (wg * 2 + ((g >> 1) & 1)) * 512 + (mb * 16 + 4 * (warp & 3) + (g >> 2)) * 2 + (g & 1), lane);
        mbar_wait(bar_wo, 0);
        if (wg) asm volatile("bar.sync 2, 128;" ::: "memory"); else asm volatile("bar.sync 1, 128;" ::: "memory");
        if (wg) mbar_wait(bar_pv, 0);
        TSTAMP2(2); CSA(8);
#pragma unroll
        for (int q = 0; q < 8; q++) {
            uint32_t bo = wo_off(0) >> 4;
            if (q) {
                mbar_wait(bar_f2 + 64 * wg + 8 * q, 0);
                asm volatile("ld.shared.u32 %0, [%1];" : "=r"(bo) : "r"(que + 32 * wg + 4 * q) : "memory");
                bo = __shfl_sync(~0u, bo, 0);
                TSTAMP4(q);
                if (q % 3 == 1) CSA(9 + q / 3);
                if (q == 1 && (tid & 127) == 0) DBGC(29 + 8 * wg);
            }
            wgmma_fence();
#pragma unroll
            for (int j = 0; j < 5; j++) wgmma_n80(ac2, (j < 4 ? da0 : da1) + (q == 7 ? o7 : 0u) + (uint64_t)((q < 6 ? q * 640 : 0) + (j & 2) * 16 + (j & 1) * 2), (j < 4 ? db0 : db1) + bo + (uint64_t)((j & 2) * 160 + (j & 1) * 32), j || q);
            wgmma_commit();
            if (q == 0) {
                wgmma_wait<0>();
                if ((tid & 127) == 0) { mbar_arrive(bar_e2 + 16 * wg); mbar_arrive(bar_e2 + 8); }
            }
            if (q == 2 && wg) {
                wgmma_wait<1>();
                if (tid == 128) mbar_arrive(bar_e2 + 24);
            }
        }
        if ((tid & 127) == 0) DBGC(28 + wg * 8 + 7);
        TSTAMP2(3);
        wgmma_wait<0>();
        TSTAMP2(4); CSA(12);
        if (__any_sync(~0u, ac2[0] != ac2[0] || ac2[2] != ac2[2])) {
#pragma unroll
            for (int i = 0; i < 40; i++) ac2[i] = 0.f;
            uint32_t a[20], an[20];
            auto lda = [&](uint32_t (&r)[20], int h) {
#pragma unroll
                for (int u = 0; u < 4; u++)
                    asm volatile("ld.relaxed.gpu.global.v4.u32 {%0,%1,%2,%3}, [%4];" : "=r"(r[4 * u]), "=r"(r[4 * u + 1]), "=r"(r[4 * u + 2]), "=r"(r[4 * u + 3]) : "l"(ot + h * 20480 + o0 + u * 512) : "memory");
#pragma unroll
                for (int u = 0; u < 2; u++)
                    asm volatile("ld.relaxed.gpu.global.v2.u32 {%0,%1}, [%2];" : "=r"(r[16 + 2 * u]), "=r"(r[17 + 2 * u]) : "l"(ot + h * 20480 + o1 + u * 256) : "memory");
            };
            lda(an, 0);
#pragma unroll 5
            for (int k = lane; k < WOB / 16; k += 32)
                reinterpret_cast<uint4*>(stg + (sl - sbase))[k] = __ldcg(reinterpret_cast<const uint4*>(wo + hg * 8 * WOB) + k);
            __syncwarp();
#pragma unroll 1
            for (int h = 0; h < 8; h++) {
#pragma unroll 1
                for (int it = 0; it < SPIN_MAX; it++) {
                    uint32_t m = 0;
#pragma unroll
                    for (int k = 0; k < 20; k += 2) m = __vimax3_u32(m, an[k], an[k + 1]);
                    if (!__any_sync(~0u, m == ~0u)) break;
                    lda(an, h);
                }
#pragma unroll
                for (int k = 0; k < 20; k++) a[k] = an[k];
                lda(an, min(h + 1, 7));
                const uint32_t bp = h == hg ? sl : sbase + wo_off(h + (h < hg));
                const int r0 = 8 * ((lane & 7) >> 1) + 2 * (lane >> 3) + (lane & 1), r2 = 4 * ((lane & 7) >> 1) + 2 * ((lane >> 3) & 1) + (lane & 1);
#pragma unroll
                for (int n = 0; n < 10; n++) {
                    uint32_t b[12];
                    ldsm_x4_t(b, bp + (n >> 1) * 1024 + r0 * 32 + (((n ^ (r0 >> 2)) & 1) << 4));
                    ldsm_x4_t(b + 4, bp + 5120 + (n >> 1) * 1024 + r0 * 32 + (((n ^ (r0 >> 2)) & 1) << 4));
                    ldsm_x4_t(b + 8, bp + 10240 + (n >> 1) * 512 + r2 * 32 + (((n ^ (r2 >> 2)) & 1) << 4));
                    mma_bf16(ac2 + 4 * n, a[0], a[8], a[1], a[9], b[0], b[1]); mma_bf16(ac2 + 4 * n, a[2], a[10], a[3], a[11], b[2], b[3]);
                    mma_bf16(ac2 + 4 * n, a[4], a[12], a[5], a[13], b[4], b[5]); mma_bf16(ac2 + 4 * n, a[6], a[14], a[7], a[15], b[6], b[7]);
                    mma_bf16(ac2 + 4 * n, a[16], a[18], a[17], a[19], b[8], b[9]);
                }
            }
        }
#pragma unroll
        for (int j = 0; j < 10; j++)
#pragma unroll
            for (int hh = 0; hh < 2; hh++) {
                const uint32_t a = pack2(ac2[4 * j + 2 * hh], ac2[4 * j + 2 * hh + 1]);
                const __nv_bfloat162 r = __hadd2_rn(*reinterpret_cast<const __nv_bfloat162*>(&xr[j][hh]), *reinterpret_cast<const __nv_bfloat162*>(&a));
                xr[j][hh] = *reinterpret_cast<const uint32_t*>(&r);
            }
        const uint32_t so = sl + 30720;
#pragma unroll
        for (int j = 0; j < 10; j += 2) stsm_x4_t(so + trow + 1024 * j, xr[j][0], xr[j][1], xr[j + 1][0], xr[j + 1][1]);
        if (wg) asm volatile("bar.sync 2, 128;" ::: "memory"); else asm volatile("bar.sync 1, 128;" ::: "memory");
        TSTAMP2(5); CSA(13);
        if ((tid & 127) == 0) {
            fence_async_smem();
            asm volatile("cp.async.bulk.tensor.2d.global.shared::cta.bulk_group [%0, {%1, %2}], [%3];" ::"l"(&tmX1), "r"(mb * 128 + 64 * wg), "r"(hg * 80), "r"(so) : "memory");
            asm volatile("cp.async.bulk.commit_group;" ::: "memory");
        }
        __syncwarp();
        const float p0 = *(volatile const float*)&rw[g].x, p1 = *(volatile const float*)&rw[g + 8].x;
        float s[3][4] = {};
        const uint32_t pp[2] = {__byte_perm(__float_as_uint(p0), 0, 0x3232), __byte_perm(__float_as_uint(p1), 0, 0x3232)};
#pragma unroll
        for (int j = 0; j < 10; j += 2) {
            const uint32_t d0 = sub2(xr[j][0], pp[0]), d1 = sub2(xr[j][1], pp[1]), d2 = sub2(xr[j + 1][0], pp[0]), d3 = sub2(xr[j + 1][1], pp[1]);
            mma_bf16(s[0], xr[j][0], xr[j][1], xr[j + 1][0], xr[j + 1][1], 0x3f803f80u, 0x3f803f80u);
            mma_bf16(s[1], d0, d1, d2, d3, d0, d2);
            mma_bf16(s[2], d0, d1, d2, d3, d1, d3);
        }
        if (t == (g >> 1)) {
            float2* rp = rsum + ri;
            constexpr float idm = 1.0f / DM;
            asm volatile("red.relaxed.gpu.global.add.v2.f32 [%0], {%1, %2};" ::"l"(rp), "f"(fmaf(-80.f, p0, s[0][0]) * idm), "f"(((g & 1) ? s[1][1] : s[1][0]) * idm) : "memory");
            asm volatile("red.relaxed.gpu.global.add.v2.f32 [%0], {%1, %2};" ::"l"(rp + 4), "f"(fmaf(-80.f, p1, s[0][2]) * idm), "f"(((g & 1) ? s[2][3] : s[2][2]) * idm) : "memory");
        }
        asm volatile("cp.async.bulk.wait_group.read 0;" ::: "memory");
        TSTAMP2(6); CSA(14); CSA_END;
        if (tid == 0) DBGC(63);
        if (tid == 128) DBGC(28);
        if (tid == 0) DBGCAL(2);
        GSTAMP(g_tim1, 14);
        SPAN(1 + 4 * layer, 3);
    }
#undef layer
}

static int h_nsm;
static void* h_sym[11];
static TileTab h_tab[2];
static CUtensorMap h_tmX0, h_tmX1, h_tmR0, h_tmR1, h_tmX1st, h_tmOut;
static KgMaps h_tmW;
typedef CUresult (*PFN_encodeTiled)(CUtensorMap*, CUtensorMapDataType, cuuint32_t, void*, const cuuint64_t*, const cuuint64_t*,
                                    const cuuint32_t*, const cuuint32_t*, CUtensorMapInterleave, CUtensorMapSwizzle,
                                    CUtensorMapL2promotion, CUtensorMapFloatOOBfill);
static void make_tmap(CUtensorMap* tm, const void* ptr, uint64_t cols, uint64_t rows, uint32_t bc, uint32_t br, CUtensorMapSwizzle sw, uint64_t pitch = 0, uint64_t hi = 0, uint32_t bh = 2) {
    static PFN_encodeTiled fn = nullptr;
    if (!fn) {
        void* p = nullptr; cudaDriverEntryPointQueryResult qr;
        cudaGetDriverEntryPoint("cuTensorMapEncodeTiled", &p, cudaEnableDefault, &qr);
        fn = (PFN_encodeTiled)p;
    }
    if (br == 0) {
        cuuint64_t dims[5] = {16, 2, rows / 8, 4, cols / 16}; cuuint64_t strides[4] = {cols * 2, cols * 16, cols * 4, 32};
        cuuint32_t box[5] = {16, 2, bc, 4, 5}; cuuint32_t es[5] = {1, 1, 1, 1, 1};
        fn(tm, CU_TENSOR_MAP_DATA_TYPE_BFLOAT16, 5, const_cast<void*>(ptr), dims, strides, box, es, CU_TENSOR_MAP_INTERLEAVE_NONE, sw,
           CU_TENSOR_MAP_L2_PROMOTION_L2_128B, CU_TENSOR_MAP_FLOAT_OOB_FILL_NONE);
        return;
    }
    if (hi == 16) {
        cuuint64_t dims[4] = {16, 32, 120, 20}; cuuint64_t strides[3] = {3840, 32, 32 * 3840};
        cuuint32_t box[4] = {16, 32, 5, 2}; cuuint32_t es[4] = {1, 1, 1, 1};
        fn(tm, CU_TENSOR_MAP_DATA_TYPE_BFLOAT16, 4, const_cast<void*>(ptr), dims, strides, box, es, CU_TENSOR_MAP_INTERLEAVE_NONE, sw,
           CU_TENSOR_MAP_L2_PROMOTION_L2_128B, CU_TENSOR_MAP_FLOAT_OOB_FILL_NONE);
        return;
    }
    if (bh == 0) {
        cuuint64_t dims[5] = {64, 64, 2, 16, 10}; cuuint64_t strides[4] = {pitch * 2, hi * 2, cols * 2, rows * 2};
        cuuint32_t box[5] = {64, 64, 2, 1, 1}; cuuint32_t es[5] = {1, 1, 1, 1, 1};
        fn(tm, CU_TENSOR_MAP_DATA_TYPE_BFLOAT16, 5, const_cast<void*>(ptr), dims, strides, box, es, CU_TENSOR_MAP_INTERLEAVE_NONE, sw,
           CU_TENSOR_MAP_L2_PROMOTION_L2_128B, CU_TENSOR_MAP_FLOAT_OOB_FILL_NONE);
        return;
    }
    if (hi) {
        cuuint64_t dims[3] = {cols, rows, hi == 64 ? 32u : 2u}; cuuint64_t strides[2] = {pitch * 2, hi * 2};
        cuuint32_t box[3] = {bc, br, bh}; cuuint32_t es[3] = {1, 1, 1};
        fn(tm, CU_TENSOR_MAP_DATA_TYPE_BFLOAT16, 3, const_cast<void*>(ptr), dims, strides, box, es, CU_TENSOR_MAP_INTERLEAVE_NONE, sw,
           CU_TENSOR_MAP_L2_PROMOTION_L2_128B, CU_TENSOR_MAP_FLOAT_OOB_FILL_NONE);
        return;
    }
    cuuint64_t dims[2] = {cols, rows}; cuuint64_t strides[1] = {(pitch ? pitch : cols) * 2};
    cuuint32_t box[2] = {bc, br}; cuuint32_t es[2] = {1, 1};
    fn(tm, CU_TENSOR_MAP_DATA_TYPE_BFLOAT16, 2, const_cast<void*>(ptr), dims, strides, box, es, CU_TENSOR_MAP_INTERLEAVE_NONE, sw,
       CU_TENSOR_MAP_L2_PROMOTION_L2_128B, CU_TENSOR_MAP_FLOAT_OOB_FILL_NONE);
}
template <typename... Args>
static void launch_pdl(void (*kern)(Args...), int grid, int block, int smem, Args... args) {
    cudaLaunchConfig_t cfg = {};
    cfg.gridDim = dim3(grid); cfg.blockDim = dim3(block); cfg.dynamicSmemBytes = smem; cfg.stream = cudaStreamPerThread;
    cudaLaunchAttribute at[1];
    at[0].id = cudaLaunchAttributeProgrammaticStreamSerialization; at[0].val.programmaticStreamSerializationAllowed = 1;
    cfg.attrs = at; cfg.numAttrs = 1;
    cudaLaunchKernelEx(&cfg, kern, args...);
}
static void launch_stage(int k, void* const* d_in, void* d_out) {
    const Par par = {k > 1 ? nullptr : (const bf16*)d_in[4], (const bf16*)d_in[5], (const bf16*)d_in[6], (const bf16*)d_in[7], (const bf16*)d_in[8], (const bf16*)d_in[9], k > 1, 0, (const bf16*)d_in[0],
                     (uint4*)h_sym[4], (uint4*)h_sym[2], (uint4*)h_sym[6], (uint4*)h_sym[3], (uint4*)h_sym[0], (float*)h_sym[5], (uint4*)h_sym[1], (const bf16*)d_in[1], (const bf16*)d_in[2]};
    auto a1 = h_nsm == 132 ? a1_kernel<true> : a1_kernel<false>;
    switch (k) {
        case 1: a1<<<h_nsm, A1_THREADS, A1_SMEM, cudaStreamPerThread>>>(par, h_tmX0, h_tmR0, h_tmX1st, h_tmW, h_tab[0]); break;
        case 3: launch_pdl(conv_kernel, DM / CV_CPB, CV_THREADS, CV_SMEM, 0, (const uint4*)h_sym[7], (const float4*)h_sym[4], (const bf16*)h_sym[8], (bf16*)h_sym[9], (const uint4*)h_sym[0], h_tmOut); break;
        case 5: launch_pdl(a1, h_nsm, A1_THREADS, A1_SMEM, par, h_tmX1, h_tmR1, h_tmX1st, h_tmW, h_tab[1]); break;
        case 7: launch_pdl(conv_kernel, DM / CV_CPB, CV_THREADS, CV_SMEM, 1, (const uint4*)h_sym[7] + SEQ / 8, (const float4*)h_sym[4] + SEQ / 2, (const bf16*)h_sym[8], (bf16*)h_sym[10], (const uint4*)h_sym[0], h_tmOut); break;
        default: break;
    }
}
static int n_stage_kernels() { return 9; }
static const char* stage_name(int k) { const char* n[] = {"kgen", "a1", "a2", "conv", "tr", "a1", "a2", "conv", "tr"}; return n[k]; }

extern "C" void kernel_launch(void* const* d_in, const int* in_sizes, int n_in, void* d_out, int out_size) {
    (void)in_sizes; (void)n_in; (void)out_size;
    static const void *p_in = nullptr, *p_w1 = nullptr, *p_w2 = nullptr, *p_out = nullptr;
    if (p_in != d_in[0] || p_w1 != d_in[1] || p_w2 != d_in[2] || p_out != d_out) {
        cudaFuncSetAttribute(conv_kernel, cudaFuncAttributeMaxDynamicSharedMemorySize, CV_SMEM);
        cudaFuncSetAttribute(a1_kernel<true>, cudaFuncAttributeMaxDynamicSharedMemorySize, A1_SMEM);
        cudaFuncSetAttribute(a1_kernel<false>, cudaFuncAttributeMaxDynamicSharedMemorySize, A1_SMEM);
        int dev; cudaGetDevice(&dev); cudaDeviceGetAttribute(&h_nsm, cudaDevAttrMultiProcessorCount, dev);
        if (h_nsm != 132) h_nsm = 128;
        cudaGetSymbolAddress(&h_sym[0], g_tap); cudaGetSymbolAddress(&h_sym[1], g_wq); cudaGetSymbolAddress(&h_sym[2], g_wo);
        cudaGetSymbolAddress(&h_sym[3], g_halo); cudaGetSymbolAddress(&h_sym[4], g_sum); cudaGetSymbolAddress(&h_sym[5], g_csp); cudaGetSymbolAddress(&h_sym[6], g_of);
        cudaGetSymbolAddress(&h_sym[7], g_piv); cudaGetSymbolAddress(&h_sym[8], g_x1T); cudaGetSymbolAddress(&h_sym[9], g_xcT); cudaGetSymbolAddress(&h_sym[10], g_yT);
        for (int i = 0; i < 264; i++) {
            const int s = i % 132, h = (s - 64) >> 1;
            const int t = h_nsm != 132 ? s : s < 64 ? ((s >> 1) & 7) * 16 + (s >> 4) * 2 + (s & 1) : s < 120 ? (1 + h % 7) * 16 + 8 + (h / 7) * 2 + (s & 1) : s < 124 ? 128 : s - 116;
            const int hg = (4 * (t >> 6) + (t & 3)) & 7;
            const uint64_t wp = (uint64_t)h_sym[1] + hg * 10 * WQ_STAGE;
            h_tab[i / 132].e[s] = make_uint4((uint32_t)wp, (uint32_t)(wp >> 32), ((t >> 2) & 15) | (i / 132) << 4 | hg << 8 | 5 * (hg >> 2) << 16 | (uint32_t)t << 24, 0);
        }
        void *px1, *px2;
        cudaGetSymbolAddress(&px1, g_x1T); cudaGetSymbolAddress(&px2, g_xcT);
        make_tmap(&h_tmX0, d_in[0], 128 * 640, 64, 64, 64, CU_TENSOR_MAP_SWIZZLE_128B, 1280, 640, 0);
        make_tmap(&h_tmX1, px2, 128, 64 * XCP, 64, 64, CU_TENSOR_MAP_SWIZZLE_128B, XCP, 64, 0);
        make_tmap(&h_tmR0, d_in[0], 640, 1024, 80, 64, CU_TENSOR_MAP_SWIZZLE_NONE, 1280, 640, 1);
        make_tmap(&h_tmR1, px2, 64, 640, 64, 80, CU_TENSOR_MAP_SWIZZLE_128B, XCP, 64, 1);
        make_tmap(&h_tmX1st, px1, 2048, 640, 64, 80, CU_TENSOR_MAP_SWIZZLE_128B, XCP);
        make_tmap(&h_tmW.q, d_in[1], 16, 640, 16, 32, CU_TENSOR_MAP_SWIZZLE_32B, 1920, 16, 5);
        make_tmap(&h_tmW.o, d_in[2], 640, 640, 4, 0, CU_TENSOR_MAP_SWIZZLE_32B);
        make_tmap(&h_tmW.t, d_in[2], 640, 640, 2, 0, CU_TENSOR_MAP_SWIZZLE_32B);
        make_tmap(&h_tmOut, d_out, 640, 1024, 80, 8, CU_TENSOR_MAP_SWIZZLE_NONE, 1280, 640, 1);
        p_in = d_in[0]; p_w1 = d_in[1]; p_w2 = d_in[2]; p_out = d_out;
    }
    for (int k = 0; k < n_stage_kernels(); k++) launch_stage(k, d_in, d_out);
}
```

```cpp
#include <cuda_runtime.h>
#include <cuda_bf16.h>
#include <cuda_fp16.h>
#include <stdint.h>
#include <cuda.h>

typedef __nv_bfloat16 bf16;

constexpr int SEQ = 2048;
constexpr int DM = 640;
constexpr int NMODE = 192;

__device__ __forceinline__ float bf2f(bf16 v) { return __bfloat162float(v); }
__device__ __forceinline__ float rbf(float v) {
    uint32_t r;
    asm("cvt.rn.bf16x2.f32 %0, %1, %2;" : "=r"(r) : "f"(v), "f"(0.f));
    return __uint_as_float(r);
}
__device__ __forceinline__ uint32_t pack2(float lo, float hi) {
    __nv_bfloat162 t = __floats2bfloat162_rn(lo, hi);
    return *reinterpret_cast<uint32_t*>(&t);
}
__device__ __forceinline__ void pdl_sync() {
    asm volatile("griddepcontrol.wait;" ::: "memory");
    asm volatile("griddepcontrol.launch_dependents;" ::: "memory");
}
__device__ __forceinline__ void pause(uint32_t n) { uint32_t c0, c1; asm volatile("mov.u32 %0, %clock;" : "=r"(c0) :: "memory"); do asm volatile("mov.u32 %0, %clock;" : "=r"(c1) :: "memory"); while (c1 - c0 < n); }
__device__ __forceinline__ float sqrt_apx(float v) { float r; asm("sqrt.approx.ftz.f32 %0, %1;" : "=f"(r) : "f"(v)); return r; }
__device__ __forceinline__ float rcp_apx(float v) { float r; asm("rcp.approx.ftz.f32 %0, %1;" : "=f"(r) : "f"(v)); return r; }
__device__ __forceinline__ uint32_t smem_u32(const void* p) { return (uint32_t)__cvta_generic_to_shared(p); }

constexpr int TAPB = 2944, TAPE = 928;
__device__ __align__(128) uint4 g_tap[DM * TAPB / 16];
#define XPAD 64
constexpr int XCP = SEQ + XPAD;
__device__ __align__(128) bf16 g_x1T[DM * XCP];
__device__ __align__(128) bf16 g_xcT[DM * XCP];
__device__ __align__(128) uint4 g_of[128 * 1280];
constexpr int WQ_STAGE = 240 * 128, WOB = 80 * 160;
__device__ __align__(128) uint4 g_wq[8 * 10 * WQ_STAGE / 16];
__device__ __align__(128) uint4 g_wo[64 * WOB / 16];
__device__ __align__(128) uint4 g_xb[128 * 240];
__device__ __align__(16) float g_csp[10 * 1920];
#define FSTR 32
__device__ __align__(128) float2 g_sum[2 * SEQ + 256 * FSTR];
__device__ __align__(16) bf16 g_piv[2 * SEQ];
__device__ __align__(128) bf16 g_yT[DM * XCP];
__device__ uint32_t g_epoch;
__device__ __align__(16) unsigned long long g_rstat[SEQ];
__device__ __align__(128) uint4 g_halo[640 * 148];
__device__ __forceinline__ unsigned long long tagw(uint32_t payload, uint32_t tag) { return ((unsigned long long)tag << 32) | payload; }
__device__ __forceinline__ ulonglong2 ld_tag2(const ulonglong2* p) {
    ulonglong2 v;
    asm volatile("ld.relaxed.gpu.global.v2.u64 {%0, %1}, [%2];" : "=l"(v.x), "=l"(v.y) : "l"(p) : "memory");
    return v;
}
__device__ __forceinline__ bool tag_ok(ulonglong2 v, uint32_t tag) { return (uint32_t)(v.x >> 32) == tag && (uint32_t)(v.y >> 32) == tag; }
__device__ __forceinline__ uint32_t ld_epoch() { uint32_t v; asm volatile("ld.relaxed.gpu.global.u32 %0, [%1];" : "=r"(v) : "l"(&g_epoch) : "memory"); return v + 1; }
constexpr int SPIN_MAX = 1 << 20;
__device__ __align__(128) uint32_t g_started[11 * 32];
__device__ __forceinline__ void sm_started(int slot) { asm volatile("red.relaxed.gpu.global.add.u32 [%0], 1;" ::"l"(g_started + slot) : "memory"); }
__device__ __forceinline__ void publish(int slot) {
    asm volatile("fence.proxy.async.global;" ::: "memory");
    asm volatile("red.release.gpu.global.add.u32 [%0], 1;" ::"l"(g_started + slot) : "memory");
}
__device__ __forceinline__ void await_all(int slot, uint32_t want) {
#pragma unroll 1
    for (int it = 0; it < SPIN_MAX; it++) {
        uint32_t v;
        asm volatile("ld.acquire.gpu.global.u32 %0, [%1];" : "=r"(v) : "l"(g_started + slot) : "memory");
        if (__all_sync(~0u, (int)(v - want) >= 0)) break;
        __nanosleep(50);
    }
    asm volatile("fence.proxy.async.global;" ::: "memory");
}
__device__ __noinline__ void sm_idle(int slot) {
    if (threadIdx.x != 288) return;
    asm volatile("fence.acq_rel.gpu;" ::: "memory");
    asm volatile("fence.proxy.async.global;" ::: "memory");
    sm_started(slot);
    const uint32_t want = ld_epoch() * gridDim.x;
    pdl_sync();
#pragma unroll 1
    for (int it = 0; it < SPIN_MAX; it++) {
        uint32_t v;
        asm volatile("ld.relaxed.gpu.global.u32 %0, [%1];" : "=r"(v) : "l"(g_started + slot) : "memory");
        if ((int)(v - want) >= 0) break;
        __nanosleep(100);
    }
}
struct TileTab { uint4 e[132]; };
__device__ __forceinline__ bool elect() {
    uint32_t p;
    asm volatile("{\n.reg .pred p;\nelect.sync _|p, 0xffffffff;\nselp.b32 %0, 1, 0, p;\n}" : "=r"(p));
    return p;
}
#define DBG_SYMS
#define TSTAMP(i)
#define TSTAMP1(i)
#define TSTAMP1T(i, t)
#define TSTAMP1X(i, t)
#define SPAN(k, i)
#define GSTAMP(arr, i)
#define TSTAMP2(i)
#define TSTAMP3(i)
#define TSTAMP4(i)
#define TSTAMPK(i, t)
#define TSTAMPC(i)
#define DBGC(i)
#define DBGV(i, v)
#define DBGCAL(i)

#define CSK(i)
#define CSK_END
#define CSA(i)
#define CSA_END
#define CST(i)
#define CST_END
#define CST_EXTRA 0
__device__ __forceinline__ void mma_bf16(float* d, uint32_t a0, uint32_t a1, uint32_t a2, uint32_t a3, uint32_t b0, uint32_t b1) {
    asm volatile("mma.sync.aligned.m16n8k16.row.col.f32.bf16.bf16.f32 {%0,%1,%2,%3}, {%4,%5,%6,%7}, {%8,%9}, {%0,%1,%2,%3};"
                 : "+f"(d[0]), "+f"(d[1]), "+f"(d[2]), "+f"(d[3]) : "r"(a0), "r"(a1), "r"(a2), "r"(a3), "r"(b0), "r"(b1));
}
__device__ __forceinline__ void mma_bf16_k8(float* d, uint32_t a0, uint32_t a1, uint32_t b0) {
    asm volatile("mma.sync.aligned.m16n8k8.row.col.f32.bf16.bf16.f32 {%0,%1,%2,%3}, {%4,%5}, {%6}, {%0,%1,%2,%3};"
                 : "+f"(d[0]), "+f"(d[1]), "+f"(d[2]), "+f"(d[3]) : "r"(a0), "r"(a1), "r"(b0));
}
__device__ __forceinline__ void ldsm_x4(uint32_t* r, uint32_t addr) {
    asm volatile("ldmatrix.sync.aligned.m8n8.x4.shared.b16 {%0,%1,%2,%3}, [%4];"
                 : "=r"(r[0]), "=r"(r[1]), "=r"(r[2]), "=r"(r[3]) : "r"(addr));
}

__device__ __forceinline__ void ldsm_x4_t(uint32_t* r, uint32_t addr) {
    asm volatile("ldmatrix.sync.aligned.m8n8.x4.trans.shared.b16 {%0,%1,%2,%3}, [%4];"
                 : "=r"(r[0]), "=r"(r[1]), "=r"(r[2]), "=r"(r[3]) : "r"(addr));
}
__device__ __forceinline__ void mbar_init(uint32_t bar, int count) { asm volatile("mbarrier.init.shared::cta.b64 [%0], %1;" ::"r"(bar), "r"(count)); }
__device__ __forceinline__ void mbar_arrive(uint32_t bar) { asm volatile("mbarrier.arrive.shared::cta.b64 _, [%0];" ::"r"(bar) : "memory"); }
__device__ __forceinline__ void mbar_wait(uint32_t bar, uint32_t parity) {
    asm volatile("{\n.reg .pred p;\nWAIT_LOOP:\n"
                 "mbarrier.try_wait.parity.shared::cta.b64 p, [%0], %1;\n"
                 "@p bra.uni WAIT_DONE;\nbra.uni WAIT_LOOP;\nWAIT_DONE:\n}" ::"r"(bar), "r"(parity) : "memory");
}

__device__ __forceinline__ void mbar_expect_tx(uint32_t bar, uint32_t bytes) {
    asm volatile("mbarrier.arrive.expect_tx.shared::cta.b64 _, [%0], %1;" ::"r"(bar), "r"(bytes) : "memory");
}
__device__ __forceinline__ void tma_load_2d(uint32_t dst, const void* tmap, int c0, int c1, uint32_t bar) {
    asm volatile("cp.async.bulk.tensor.2d.shared::cluster.global.mbarrier::complete_tx::bytes [%0], [%1, {%3, %4}], [%2];"
                 ::"r"(dst), "l"(tmap), "r"(bar), "r"(c0), "r"(c1) : "memory");
}
__device__ __forceinline__ void tma_load_3d(uint32_t dst, const void* tmap, int c0, int c1, int c2, uint32_t bar) {
    asm volatile("cp.async.bulk.tensor.3d.shared::cluster.global.mbarrier::complete_tx::bytes [%0], [%1, {%3, %4, %5}], [%2];"
                 ::"r"(dst), "l"(tmap), "r"(bar), "r"(c0), "r"(c1), "r"(c2) : "memory");
}
__device__ __forceinline__ void fence_async_smem() { asm volatile("fence.proxy.async.shared::cta;" ::: "memory"); }
__device__ __forceinline__ void bulk_load(uint32_t dst, const void* src, uint32_t bytes, uint32_t bar) {
    asm volatile("cp.async.bulk.shared::cluster.global.mbarrier::complete_tx::bytes [%0], [%1], %2, [%3];"
                 ::"r"(dst), "l"(src), "r"(bytes), "r"(bar) : "memory");
}
__device__ __forceinline__ void stsm_x4(uint32_t addr, uint32_t r0, uint32_t r1, uint32_t r2, uint32_t r3) {
    asm volatile("stmatrix.sync.aligned.m8n8.x4.shared.b16 [%0], {%1,%2,%3,%4};" ::"r"(addr), "r"(r0), "r"(r1), "r"(r2), "r"(r3) : "memory");
}
__device__ __forceinline__ void stsm_x4_t(uint32_t addr, uint32_t r0, uint32_t r1, uint32_t r2, uint32_t r3) {
    asm volatile("stmatrix.sync.aligned.m8n8.x4.trans.shared.b16 [%0], {%1,%2,%3,%4};" ::"r"(addr), "r"(r0), "r"(r1), "r"(r2), "r"(r3) : "memory");
}
__device__ __forceinline__ void prefetch_tmap(const void* tmap) { asm volatile("prefetch.tensormap [%0];" ::"l"(tmap) : "memory"); }

__device__ __forceinline__ float2 cexp_at(float wr2, float wi, float p) {
    float er;
    asm("ex2.approx.ftz.f32 %0, %1;" : "=f"(er) : "f"(wr2 * p));
    float th = wi * p;
    const float k = rintf(th * 0.15915494309189535f);
    th = fmaf(k, -6.2831854820251465f, th);
    th = fmaf(k, 1.7484555314695172e-7f, th);
    return make_float2(er * __cosf(th), er * __sinf(th));
}
__device__ __forceinline__ float2 cmul(float2 a, float2 b) {
    return make_float2(fmaf(a.x, b.x, -a.y * b.y), fmaf(a.x, b.y, a.y * b.x));
}
__device__ __forceinline__ float2 csqr(float2 a) { return make_float2(fmaf(a.x, a.x, -a.y * a.y), (a.x + a.x) * a.y); }
__device__ __forceinline__ uint32_t packh(float2 v) {
    uint32_t r;
    asm("cvt.rn.f16x2.f32 %0, %1, %2;" : "=r"(r) : "f"(v.y), "f"(v.x));
    return r;
}
__device__ __forceinline__ uint2 packr(float2 v) { return make_uint2(packh(v), packh(make_float2(-v.y, v.x))); }
__device__ __forceinline__ uint32_t hcmul(uint32_t a, uint2 b) {
    const __half2 x = *reinterpret_cast<const __half2*>(&a);
    const __half2 r = __hfma2(__high2half2(x), *reinterpret_cast<const __half2*>(&b.y), __hmul2(__low2half2(x), *reinterpret_cast<const __half2*>(&b.x)));
    return *reinterpret_cast<const uint32_t*>(&r);
}

struct Par { const bf16 *logA, *Aim, *Cre, *Cim, *logdt, *dsk; int layer, pad; const bf16* x; uint4 *sum, *wop, *of, *halo, *tap; float* csp; uint4* wq; const bf16 *wqkv, *wo; };
struct KgMaps { CUtensorMap q, o, t; };

__device__ __forceinline__ void bulk_prefetch(const void* p, uint32_t bytes) { asm volatile("cp.async.bulk.prefetch.L2.global [%0], %1;" ::"l"(p), "r"(bytes) : "memory"); }
__device__ __forceinline__ void bulk_store(void* dst, uint32_t src, uint32_t bytes) { asm volatile("cp.async.bulk.global.shared::cta.bulk_group [%0], [%1], %2;" ::"l"(dst), "r"(src), "r"(bytes) : "memory"); }
__device__ __forceinline__ void kgen_first(const Par& in, const KgMaps& tm, const uint32_t b0, const uint32_t wbar, const bool one) {
    const uint32_t blk = blockIdx.x, sec = (blk >= 40) + (blk >= 80), it = (blk >> 3) - 5 * sec, up = (blk >> 2) & 1, hi = blk >> 6;
    auto fetch = [&](int h) {
        if (blk < 120) asm volatile("cp.async.bulk.tensor.4d.shared::cluster.global.mbarrier::complete_tx::bytes [%0], [%1, {%3, %3, %4, %5}], [%2];"
                                    ::"r"(b0 + 10240 * h), "l"(&tm.q), "r"(wbar + 8 * h), "r"(0), "r"(sec * 40 + (blk & 7) * 5), "r"(2 * it + 10 * (up ^ h)) : "memory");
    };
    auto fetch_o = [&](int i) {
        asm volatile("cp.async.bulk.tensor.5d.shared::cluster.global.mbarrier::complete_tx::bytes [%0], [%1, {%3, %3, %4, %3, %5}], [%2];"
                     ::"r"(b0 + 20480 + i * 5120), "l"(&tm.o + i), "r"(wbar + 16), "r"(0), "r"((blk & 7) * 10 + (hi + i) * 4), "r"(((blk >> 3) & 7) * 5) : "memory");
    };
    if (one) {
#pragma unroll
        for (int i = 0; i < 3; i++) mbar_init(wbar + 8 * i, 1);
        asm volatile("fence.mbarrier_init.release.cluster;" ::: "memory");
        fetch(0);
    }
    __syncwarp();
    if (blk >> 20) __trap();
    if (one) {
        bulk_prefetch(in.wqkv + blk * 9600, 19200);
        fetch(1);
        bulk_prefetch(in.wo + blk * 3200, 6400);
        fetch_o(0);
        if (hi) fetch_o(1);
        mbar_expect_tx(wbar, 10240); mbar_expect_tx(wbar + 8, 10240); mbar_expect_tx(wbar + 16, 5120 + hi * 2560);
        bulk_prefetch(in.x + blk * 10240, 20480);
    }
}
__device__ __forceinline__ void kgen_side(const Par& in, const uint32_t b0, const uint32_t wbar) {
    const uint32_t blk = blockIdx.x, sec = (blk >= 40) + (blk >= 80), it = (blk >> 3) - 5 * sec, cg = (blk >> 3) & 7, hb = blk & 7;
    unsigned char* dst = reinterpret_cast<unsigned char*>(in.wq) + (hb * 10 + it) * WQ_STAGE + sec * 5120;
    if (blk < 120) {
        mbar_wait(wbar, 0);
        CSK(2);
        bulk_store(dst, b0, 5120); bulk_store(dst + 15360, b0 + 5120, 5120);
        mbar_wait(wbar + 8, 0);
        CSK(3);
        bulk_store(dst + 5 * WQ_STAGE, b0 + 10240, 5120); bulk_store(dst + 5 * WQ_STAGE + 15360, b0 + 15360, 5120);
        asm volatile("cp.async.bulk.commit_group;" ::: "memory");
        asm volatile("cp.async.bulk.wait_group 0;" ::: "memory");
        CSK(4);
        publish(96 + 32 * hb);
        CSK(5);
    }
    if (blk < 128) {
        mbar_wait(wbar + 16, 0);
        bulk_store(reinterpret_cast<unsigned char*>(in.wop) + (cg * 8 + (hb == cg ? 0 : hb + (hb < cg))) * WOB + (blk >> 6) * 5120, b0 + 20480, blk < 64 ? 5120 : 7680);
        asm volatile("cp.async.bulk.commit_group;" ::: "memory");
    }
}
__device__ __forceinline__ void kgen_sums(const Par& in, const uint32_t b0, const int h) {
    const int lane = threadIdx.x & 31, blk = blockIdx.x;
    if (blk < 120) {
        float cs[5][4] = {};
#pragma unroll
        for (int a = 0; a < 4; a++)
#pragma unroll
            for (int j = 0; j < 5; j++) {
                uint32_t w[4];
                ldsm_x4_t(w, b0 + h * 10240 + j * 1024 + ((lane >> 4) * 8 + (lane & 7)) * 32 + ((((lane >> 3) ^ (lane >> 2)) & 1) << 4) + (a >> 1) * 5120 + (a & 1) * 512);
                mma_bf16(cs[j], w[0], w[1], w[2], w[3], 0x3f803f80u, 0x3f803f80u);
            }
#pragma unroll
        for (int j = 0; j < 5; j++)
            if ((lane & 3) < 2) in.csp[(blk + 120 * h) * 80 + j * 16 + (lane >> 2) + 8 * (lane & 3)] = (lane & 3) ? cs[j][2] : cs[j][0];
    }
}
struct KgPar { uint32_t pw[4], ph[4], pdt, pdsk; };
__device__ __forceinline__ void kgen_load(const Par& in, const bf16* logA, const int w11, KgPar& k) {
    const uint32_t o = blockIdx.x * 480 + min(w11 * 48, w11 * 32 + 128), ow = o + (threadIdx.x & 31), oh = o + ow + (w11 < 8 ? 64 : 0);
    k.pdt = reinterpret_cast<const unsigned short*>(in.logdt)[ow / 96];
    k.pdsk = reinterpret_cast<const unsigned short*>(in.dsk)[ow / 96];
#pragma unroll
    for (int i = 0; i < 4; i++) {
        const bf16* p = i == 0 ? logA : i == 1 ? in.Aim : i == 2 ? in.Cre : in.Cim;
        k.pw[i] = reinterpret_cast<const uint32_t*>(p)[ow]; k.ph[i] = reinterpret_cast<const unsigned short*>(p)[oh];
    }
}
__device__ __forceinline__ void kgen_tables(const Par& in, uint4* tabs, const int w11, const KgPar& kp) {
    const int lane = threadIdx.x & 31, grp = min(w11 >> 1, 4), warp = w11 - 2 * grp;
    const int blk = blockIdx.x, d = blk * 5 + grp, tid = warp * 32 + lane;
    uint4* tab = tabs + grp * (2 * 256);
    const uint32_t *pw = kp.pw, *ph = kp.ph;
#pragma unroll
    for (int i = 0; i < 3; i++)
        if (i < 2 || w11 * 32 + lane < 36) asm volatile("st.global.v4.u32 [%0], {%1,%1,%1,%1};" ::"l"(in.halo + blk * 740 + w11 * 32 + lane + 352 * i), "r"(~0u));
    __syncwarp();
    if (w11 == 10) {
        if (lane < 16) in.sum[blk * 16 + lane] = make_uint4(0, 0, 0, 0);
        else if (lane < 20) reinterpret_cast<uint32_t*>(in.sum + 2048)[(blk * 4 + lane - 16) * FSTR] = 0;
    } else if (w11 > 1) asm volatile("bar.arrive 9, 352;" ::: "memory");
#pragma unroll
    for (int i = 0; i < 6; i++) tabs[w11 * 256 + 32 * i + lane] = make_uint4(0, 0, 0, 0);
    __syncwarp();
    CSK(1);
    const uint32_t tw = smem_u32(tabs) + w11 * 4096;
    const int g = lane >> 2, t = lane & 3;
    const int mt = lane >> 3, r = lane & 7;
    const uint32_t st1 = tw + mt * 1024 + r * 16, st2 = tw + (mt & 1) * 1024 + (mt >> 1) * 128 + ((r ^ (mt >> 1)) << 4), st3 = tw + 2048 + mt * 128 + ((r ^ mt) << 4);
    const uint32_t lda = tw + (mt & 1) * 1024 + r * 128 + (((mt >> 1) ^ r) << 4), ldb = tw + (mt >> 1) * 1024 + r * 128 + (((mt & 1) ^ r) << 4), ldc = tw + 2048 + r * 128 + ((mt ^ r) << 4);
    auto ldsm = [](uint32_t* v, uint32_t a) {
        asm volatile("ldmatrix.sync.aligned.m8n8.x4.shared.b16 {%0,%1,%2,%3}, [%4];" : "=r"(v[0]), "=r"(v[1]), "=r"(v[2]), "=r"(v[3]) : "r"(a) : "memory");
    };
    auto mma = [](float* c, const uint32_t* a, const uint32_t* b) {
        asm("mma.sync.aligned.m16n8k16.row.col.f32.f16.f16.f32 {%0,%1,%2,%3}, {%4,%5,%6,%7}, {%8,%9}, {%0,%1,%2,%3};"
            : "+f"(c[0]), "+f"(c[1]), "+f"(c[2]), "+f"(c[3]) : "r"(a[0]), "r"(a[1]), "r"(a[2]), "r"(a[3]), "r"(b[0]), "r"(b[1]));
    };
    asm volatile("st.shared.u32 [%0], %1;" ::"r"(tw + 3072), "r"(st1 ^ st2 ^ st3 ^ lda ^ ldb ^ ldc) : "memory");
    if (in.pad) __trap();
    const float dt = rbf(expf(__uint_as_float(kp.pdt << 16)));
    const uint32_t cm = __vmaxu2(__vmaxu2(pw[2] & 0x7fff7fffu, pw[3] & 0x7fff7fffu), __byte_perm(ph[2], ph[3], 0x5410) & 0x7fff7fffu);
    const int ex = min(max((int)(__float_as_uint(__uint_as_float(__reduce_max_sync(~0u, max(cm << 16, cm & 0xffff0000u))) * dt) >> 23), 20), 240);
    const float scale = __uint_as_float((uint32_t)(127 + 10 + 127 - ex) << 23), unscale = 2.0f * __uint_as_float((uint32_t)(ex - 10) << 23);
    float k2048 = 0.f;
    float acc[5][4] = {};
    uint32_t af[4][4] = {};
    auto rest = [&] {
        uint32_t b[4][4], c[8];
#pragma unroll
        for (int k = 0; k < 4; k++) {
            ldsm(b[k], ldb ^ (k << 5));
            if (!(k & 1)) ldsm(c + 2 * k, ldc ^ (k << 5));
        }
#pragma unroll
        for (int k = 0; k < 4; k++) { mma(acc[2], af[k], b[k]); mma(acc[3], af[k], b[k] + 2); mma(acc[4], af[k], c + 2 * k); }
    };
#pragma unroll 1
    for (uint32_t sel = 0x1076; sel < (grp < 4 ? 0x6000u : 0x4000u); sel += 0x2200) {
        rest();
        auto par = [&](int i) { return __uint_as_float(__byte_perm(pw[i], ph[i], sel)); };
        const float wr2 = -rbf(expf(par(0))) * dt * 1.4426950408889634f, wi = par(1) * dt;
        const float2 y1 = cexp_at(wr2, -wi, 1.f), w64 = cexp_at(wr2, wi, 64.f), y4 = csqr(csqr(y1)), z8 = csqr(make_float2(y4.x, -y4.y)), y128 = csqr(make_float2(w64.x, -w64.y));
        float2 h0 = make_float2(1.f, 0.f), g0 = make_float2(par(2) * dt * scale, -par(3) * dt * scale);
        const float2 v2 = csqr(y128), v3 = cmul(v2, y128), v4 = csqr(v2), v8 = csqr(v4), c8 = cmul(g0, v8);
        const uint2 z64 = packr(w64), v[8] = {make_uint2(packh(c8), 0u), packr(y128), packr(v2), packr(v3), packr(v4), packr(cmul(v4, y128)), packr(csqr(v3)), packr(cmul(v4, v3))};
        k2048 += fmaf(c8.x, v8.x, -c8.y * v8.y);
        uint32_t ge[4];
#pragma unroll
        for (int e = 0; e < 8; e++) {
            const uint32_t p = packh(h0), q = packh(g0);
            if (!(e & 1)) ge[e >> 1] = q;
            stsm_x4((st1 ^ (e << 4)) + e * 128, p, e ? hcmul(p, z64) : z64.x, q, hcmul(q, v[1]));
            if (e < 7) { h0 = e ? cmul(h0, z8) : z8; g0 = cmul(g0, y1); }
        }
        __syncwarp();
        uint32_t b[4][4];
#pragma unroll
        for (int k = 0; k < 4; k++) { ldsm(af[k], lda ^ (k << 5)); ldsm(b[k], (ldb ^ (k << 5)) + 2048); }
#pragma unroll
        for (int e = 0; e < 8; e += 2) {
            stsm_x4((st2 ^ (e << 4)) + e * 128, hcmul(ge[e & 3], v[2 + (e >> 2)]), hcmul(ge[0], v[4 + (e >> 1)]), hcmul(ge[(e & 3) + 1], v[2 + (e >> 2)]), hcmul(ge[2], v[4 + (e >> 1)]));
            if (!(e & 3)) stsm_x4((st3 ^ (e << 4)) + e * 128, e ? hcmul(v[0].x, v[e]) : v[0].x, hcmul(v[0].x, v[e + 1]), hcmul(v[0].x, v[e + 2]), hcmul(v[0].x, v[e + 3]));
            mma(acc[0], af[e >> 1], b[e >> 1]);
            mma(acc[1], af[e >> 1], b[e >> 1] + 2);
        }
        __syncwarp();
        if (sel == 0x1076) CSK(3);
    }
    rest();
#pragma unroll
    for (int e = 0; e < 5; e++) k2048 += __shfl_xor_sync(~0u, k2048, 1 << e);
    {
        float* Pp = reinterpret_cast<float*>(tab + warp * 256);
        auto sw = [](int i) { return i ^ ((i >> 2) & 24); };
#pragma unroll
        for (int h = 0; h < 2; h++) {
            const int b = g + 8 * h;
            *reinterpret_cast<float2*>(Pp + sw(8 * b + 2 * t)) = make_float2(acc[0][2 * h] * unscale, acc[0][2 * h + 1] * unscale);
            *reinterpret_cast<float2*>(Pp + 128 + sw(8 * b + 2 * t)) = make_float2(acc[1][2 * h] * unscale, acc[1][2 * h + 1] * unscale);
            *reinterpret_cast<float2*>(Pp + 256 + sw(4 * b + 2 * (t & 1) + 64 * (t >> 1))) = make_float2(acc[2][2 * h] * unscale, acc[2][2 * h + 1] * unscale);
            *reinterpret_cast<float2*>(Pp + 384 + sw(2 * b + 32 * t)) = make_float2(acc[3][2 * h] * unscale, acc[3][2 * h + 1] * unscale);
            Pp[512 + sw(b + 32 * t)] = acc[4][2 * h] * unscale;
            Pp[512 + sw(b + 32 * t + 16)] = acc[4][2 * h + 1] * unscale;
        }
        if (lane == 0) Pp[640] = k2048 * unscale;
    }
    CSK(4);
    asm volatile("bar.sync %0, %1;" ::"r"(grp + 4), "r"(grp < 4 ? 64 : 96) : "memory");
    if (warp == 2) return;
    const float* Kp = reinterpret_cast<const float*>(tab);
    auto ksum = [&](int i) -> float { return rbf(Kp[i] + Kp[1024 + i] + (grp < 4 ? 0.f : Kp[2048 + i])); };
    auto ksum2 = [&](int q) -> float2 {
        q ^= (q >> 2) & 12;
        const float2 a = reinterpret_cast<const float2*>(Kp)[q], b = reinterpret_cast<const float2*>(Kp)[512 + q];
        const float2 c = grp < 4 ? make_float2(0.f, 0.f) : reinterpret_cast<const float2*>(Kp)[1024 + q];
        return make_float2(a.x + b.x + c.x, a.y + b.y + c.y);
    };
    {
        uint2* W2 = reinterpret_cast<uint2*>(in.tap + d * (TAPB / 16)) + 8;
        uint2* E4 = W2 + (TAPE - 64) / 8;
        float2 v = ksum2(64 * warp + lane), z = ksum2(64 * warp + 32 + lane), y = ksum2(128 + tid);
        const int q = (96 + tid) ^ (((96 + tid) >> 2) & 6);
        const float4 ua = reinterpret_cast<const float4*>(Kp)[q], uc = reinterpret_cast<const float4*>(Kp)[256 + q], ud = grp < 4 ? make_float4(0.f, 0.f, 0.f, 0.f) : reinterpret_cast<const float4*>(Kp)[512 + q];
        const float4 ub = make_float4(uc.x + ud.x, uc.y + ud.y, uc.z + ud.z, uc.w + ud.w);
        const float s1 = ksum(tid == 31 ? 336 : lane ? 384 : 103), s2 = ksum(tid == 31 ? 512 : tid ? 640 : 231);
        if (tid == 0) v.x += __uint_as_float(kp.pdsk << 16);
        if (tid == 63) y.y -= s1;
        const uint32_t lo = pack2(v.x, v.y), hi = pack2(z.x, z.y), tp = pack2(y.x, y.y);
        uint32_t nl = __shfl_sync(~0u, lo, lane - 1), nh = __shfl_sync(~0u, lane == 31 ? lo : hi, lane - 1), nt = __shfl_sync(~0u, tp, lane + 1);
        if (lane == 0) nl = warp ? __float_as_uint(s1) : 0u;
        if (lane == 31) nt = warp ? 0u : __float_as_uint(s1) >> 16;
        W2[64 * warp + lane] = make_uint2(__byte_perm(lo, nl, 0x7610), __byte_perm(lo, 0, 0x1032));
        W2[64 * warp + lane + 32] = make_uint2(__byte_perm(hi, nh, 0x7610), __byte_perm(hi, 0, 0x1032));
        reinterpret_cast<uint4*>(W2)[64 + tid] = make_uint4(__byte_perm(tp, __float_as_uint(s2), tid ? 0x1010 : 0x7610), __byte_perm(tp, 0, 0x1010), __byte_perm(tp, 0, 0x1032), __byte_perm(nt, tp, 0x7610));
        E4[(tid < 32 ? 159 : 209 - 32) + tid] = make_uint2(pack2(ua.x + ub.x, ua.y + ub.y), pack2(ua.z + ub.z, ua.w + ub.w - (tid == 31 ? s2 : 0.f)));
        if (tid == 63) E4[241] = make_uint2(__float_as_uint(s2) >> 16, 0u);
    }
    CSK(5);
    SPAN(0, 3);
}

#define CV_SLEEP 40
#define CV_TD1 500
#define CV_TD0 0
#define CV_LD "ld.relaxed.gpu.global"
#define CV_NL 1
#define CV_D2 3
#define CV_PDH 12
#define CV_PDF 4
#define CV_HAND 7
constexpr int CV_CPB = 5;
constexpr int CV_THREADS = 512;
constexpr int UPADF = 128;
constexpr int ULEN = UPADF + SEQ;
constexpr int XLEN = XCP;
constexpr int BX_5 = 0, BX_3 = 3264, BX_9 = 6528, BX_7 = 8960, BX_LEN = 11392;
constexpr int CV_SM_U = 0;
constexpr int CV_SM_T = CV_CPB * ULEN * 2;
constexpr int CV_SM_B = CV_SM_T + CV_CPB * TAPB;
constexpr int CV_SM_X = CV_SM_B + CV_CPB * BX_LEN;
constexpr int CV_SM_Y = (CV_SM_X + CV_CPB * XLEN * 2 + 127) & ~127;
constexpr int CV_SM_CNT = CV_SM_Y + CV_CPB * 8192;
constexpr int CV_SM_O = CV_SM_CNT + 128;
constexpr int CV_SMEM = CV_SM_O + 20480 + CST_EXTRA;
static_assert(ULEN % 128 == 0 && CV_SM_B % 128 == 0 && CV_SM_CNT % 128 == 0, "layout");

__device__ __forceinline__ uint32_t sub2(uint32_t x, uint32_t m) {
    const __nv_bfloat162 d = __hsub2(*reinterpret_cast<const __nv_bfloat162*>(&x), *reinterpret_cast<const __nv_bfloat162*>(&m));
    return *reinterpret_cast<const uint32_t*>(&d);
}
__device__ __forceinline__ uint32_t add2(uint32_t x, uint32_t y) {
    const __nv_bfloat162 d = __hadd2_rn(*reinterpret_cast<const __nv_bfloat162*>(&x), *reinterpret_cast<const __nv_bfloat162*>(&y));
    return *reinterpret_cast<const uint32_t*>(&d);
}
__device__ __forceinline__ void wgmma_fence() { asm volatile("wgmma.fence.sync.aligned;" ::: "memory"); }
__device__ __forceinline__ void wgmma_commit() { asm volatile("wgmma.commit_group.sync.aligned;" ::: "memory"); }
template <int N> __device__ __forceinline__ void wgmma_wait() { asm volatile("wgmma.wait_group.sync.aligned %0;" ::"n"(N) : "memory"); }
__device__ __forceinline__ uint64_t make_desc(uint32_t addr, uint32_t lbo, uint32_t sbo, uint32_t mode) {
    return (uint64_t)((addr & 0x3FFFF) >> 4) | ((uint64_t)(lbo >> 4) << 16) | ((uint64_t)(sbo >> 4) << 32) | ((uint64_t)mode << 62);
}
__device__ __forceinline__ void wgmma_rs128(float (&d)[64], uint2 hi, uint2 lo, uint64_t db, int acc) {
    asm volatile("{\n.reg .pred p;\nsetp.ne.b32 p, %69, 0;\nwgmma.mma_async.sync.aligned.m64n128k16.f32.bf16.bf16 {%0,%1,%2,%3,%4,%5,%6,%7,%8,%9,%10,%11,%12,%13,%14,%15,%16,%17,%18,%19,%20,%21,%22,%23,%24,%25,%26,%27,%28,%29,%30,%31,%32,%33,%34,%35,%36,%37,%38,%39,%40,%41,%42,%43,%44,%45,%46,%47,%48,%49,%50,%51,%52,%53,%54,%55,%56,%57,%58,%59,%60,%61,%62,%63}, {%64,%65,%66,%67}, %68, p, 1, 1, 0;\n}"
                 : "+f"(d[0]), "+f"(d[1]), "+f"(d[2]), "+f"(d[3]), "+f"(d[4]), "+f"(d[5]), "+f"(d[6]), "+f"(d[7]), "+f"(d[8]), "+f"(d[9]), "+f"(d[10]), "+f"(d[11]), "+f"(d[12]), "+f"(d[13]), "+f"(d[14]), "+f"(d[15]), "+f"(d[16]), "+f"(d[17]), "+f"(d[18]), "+f"(d[19]), "+f"(d[20]), "+f"(d[21]), "+f"(d[22]), "+f"(d[23]), "+f"(d[24]), "+f"(d[25]), "+f"(d[26]), "+f"(d[27]), "+f"(d[28]), "+f"(d[29]), "+f"(d[30]), "+f"(d[31]), "+f"(d[32]), "+f"(d[33]), "+f"(d[34]), "+f"(d[35]), "+f"(d[36]), "+f"(d[37]), "+f"(d[38]), "+f"(d[39]), "+f"(d[40]), "+f"(d[41]), "+f"(d[42]), "+f"(d[43]), "+f"(d[44]), "+f"(d[45]), "+f"(d[46]), "+f"(d[47]), "+f"(d[48]), "+f"(d[49]), "+f"(d[50]), "+f"(d[51]), "+f"(d[52]), "+f"(d[53]), "+f"(d[54]), "+f"(d[55]), "+f"(d[56]), "+f"(d[57]), "+f"(d[58]), "+f"(d[59]), "+f"(d[60]), "+f"(d[61]), "+f"(d[62]), "+f"(d[63])
                 : "r"(hi.x), "r"(hi.y), "r"(lo.x), "r"(lo.y), "l"(db), "r"(acc));
}
template <int V> struct Int { __device__ constexpr operator int() const { return V; } };
__device__ __forceinline__ void sts4(uint32_t a, const uint32_t* v) { asm volatile("st.shared.v4.u32 [%0], {%1,%2,%3,%4};" ::"r"(a), "r"(v[0]), "r"(v[1]), "r"(v[2]), "r"(v[3]) : "memory"); }
__device__ __forceinline__ uint32_t lds1(uint32_t a) { uint32_t v; asm volatile("ld.shared.u32 %0, [%1];" : "=r"(v) : "r"(a) : "memory"); return v; }
__device__ __forceinline__ uint32_t lds1v(uint32_t a) { uint32_t v; asm volatile("ld.volatile.shared.u32 %0, [%1];" : "=r"(v) : "r"(a) : "memory"); return v; }
__device__ __forceinline__ uint4 lds4(uint32_t a) { uint4 v; asm volatile("ld.shared.v4.u32 {%0,%1,%2,%3}, [%4];" : "=r"(v.x), "=r"(v.y), "=r"(v.z), "=r"(v.w) : "r"(a) : "memory"); return v; }
__device__ __forceinline__ uint4 ldx(uint32_t a) {
    uint4 v;
    asm volatile("ld.shared.v2.u32 {%0,%1}, [%4];\nld.shared.v2.u32 {%2,%3}, [%4+128];" : "=r"(v.x), "=r"(v.y), "=r"(v.z), "=r"(v.w) : "r"(a) : "memory");
    return v;
}
__device__ __forceinline__ void cv_store(unsigned char* p, uint4 x, uint4 y) {
    asm volatile("st.relaxed.gpu.global.v2.u32 [%0], {%1,%2};" ::"l"(p), "r"(add2(x.x, __byte_perm(y.x, y.y, 0x5410))), "r"(add2(x.y, __byte_perm(y.z, y.w, 0x5410))) : "memory");
    asm volatile("st.relaxed.gpu.global.v2.u32 [%0], {%1,%2};" ::"l"(p + 128), "r"(add2(x.z, __byte_perm(y.x, y.y, 0x7632))), "r"(add2(x.w, __byte_perm(y.z, y.w, 0x7632))) : "memory");
}
__device__ __forceinline__ int usw(int ch) { return ch ^ ((ch >> 3) & 1); }
__global__ void __launch_bounds__(CV_THREADS, 1) conv_kernel(int layer, const uint4* __restrict__ piv, const float4* __restrict__ sum, const bf16* __restrict__ x1T,
                                                             bf16* __restrict__ dst, const uint4* __restrict__ tap, const __grid_constant__ CUtensorMap tmOut) {
    extern __shared__ __align__(1024) unsigned char sm[];
    SPAN(3 + 4 * layer, 0);
    bf16* Us = reinterpret_cast<bf16*>(sm + CV_SM_U);
    bf16* Xs = reinterpret_cast<bf16*>(sm + CV_SM_X);
#define CV_IDX int tid; asm volatile("mov.u32 %0, %tid.x;" : "=r"(tid)); const int lane = tid & 31, warp = __shfl_sync(~0u, tid >> 5, 0);
    const int d0 = blockIdx.x * CV_CPB, tile = blockIdx.x; (void)tile;
    const uint32_t cnt = smem_u32(sm + CV_SM_CNT);
    struct Lc { uint32_t a4, a8, uc, ud, y, e4, en, sp, ss; int go; };
    auto lane_consts = [&](int lane, int c) {
        const int mat = lane >> 3, r = lane & 7, g = lane >> 2, ti = lane & 3, e = g - 2 * ti;
        const int j2 = 13 + (r ^ 1) + 8 * (mat >> 1), j3 = j2 + 2, i0 = 8 * (mat & 1);
        const uint32_t sb = smem_u32(sm), oc = sb + usw(16 * (mat >> 1) + 2 * r + (mat & 1)) * 16;
        const Lc l = {sb + CV_SM_B + c * BX_LEN + ((j2 & 1) ? BX_3 + (4 * j2 + i0 + 84) * 2 : BX_5 + (4 * j2 + i0 + 80) * 2),
                      sb + CV_SM_B + c * BX_LEN + ((j3 & 1) ? BX_7 : BX_9) + (8 * j3 + i0 + 136) * 2,
                      oc + CV_SM_U + (c * ULEN + UPADF) * 2, sb + CV_SM_U + (c * ULEN + UPADF) * 2 + usw(16 * mat + 2 * r + 2) * 16, oc + CV_SM_Y + c * 8192,
                      sb + CV_SM_T + c * TAPB + TAPE + (307 + 2 * g - ti) * 4, sb + CV_SM_T + c * TAPB + (528 + e) * 4,
                      e == -5 ? 0x4410u : e == -4 ? 0x1044u : 0x4444u, e == 3 ? 0x4410u : e == 4 ? 0x1044u : 0x4444u,
                      c * XCP * 2 + (lane >> 4) * 256 + (lane & 15) * 8};
        asm volatile("st.shared.u32 [%0], %1;" ::"r"(sb + CV_SM_CNT + 120), "r"(l.y ^ l.a4 ^ l.a8 ^ l.uc ^ l.ud ^ l.e4 ^ l.en ^ l.sp ^ l.ss ^ l.go) : "memory");
        return l;
    };
    unsigned char* const dq = reinterpret_cast<unsigned char*>(dst + (size_t)d0 * XCP);
    auto far = [&](auto T0_, const auto& seq, const Lc& lc, int c, int lane, const uint2 (&f)[20], uint32_t kk) {
        constexpr int T0 = T0_, T1 = T0 + 6, TC = T0 > 7 ? T0 : 7, NS = sizeof(seq) / sizeof(seq[0]), PD = T0 > 7 ? CV_PDH : CV_PDF;
        uint32_t bq[28], yw[4], yz[4], P, S;
        uint4 xv, yv;
        asm("prmt.b32 %0, %1, 0, %2;" : "=r"(P) : "r"(kk), "r"(lc.sp));
        asm("prmt.b32 %0, %1, 0, %2;" : "=r"(S) : "r"(kk), "r"(lc.ss));
#pragma unroll
        for (int k = 0; 2 * k < T1 - TC + 4; k++) ldsm_x4(bq + 4 * k, lc.uc + (TC - 8) * 256 + 512 * k);
#pragma unroll
        for (int k = 0; 4 * k < T1 - TC; k++) ldsm_x4(bq + 20 + 4 * k, lc.ud + (TC - 8) * 256 + 1024 * k);
        CST(3);
        mbar_wait(cnt + 8 * c, 0);
        mbar_wait(cnt + 40, 0);
        CST(4);
        float acc[6][4] = {};
        uint32_t a[PD + 1][4];
#pragma unroll
        for (int i = -PD; i < NS + 3; i++) {
            if (i + PD < NS) ldsm_x4_t(a[(i + PD) % (PD + 1)], seq[i + PD] < 32 ? lc.a4 + (seq[i + PD] - 2) * 128 : lc.a8 + (seq[i + PD] - 34) * 256);
            if (i < 0) continue;
#pragma unroll
            for (int T = T0; T < T1; T++) {
                if (i >= NS) break;
                const int ee = seq[i] < 32 ? 2 * T - 6 - seq[i] : T + 35 - seq[i];
                if (i == 0 && T >= TC) mma_bf16(acc[T - T0], P, 0u, S, P, bq[2 * (T - TC)], bq[2 * (T - TC) + 1]);
                if (i == 1 && T >= TC) mma_bf16_k8(acc[T - T0], 0u, S, bq[20 + T - TC]);
                if (i == (T >= TC ? 2 : 0)) mma_bf16(acc[T - T0], f[19].x, 0u, f[19].y, f[19].x, bq[2 * (T - TC + 4)], bq[2 * (T - TC + 4) + 1]);
                if (seq[i] < 32 ? ee >= 0 && ee <= 9 : ee >= 10) mma_bf16(acc[T - T0], a[i % (PD + 1)][0], a[i % (PD + 1)][1], a[i % (PD + 1)][2], a[i % (PD + 1)][3], f[ee].x, f[ee].y);
            }
#pragma unroll
            for (int k = 0; k < 3; k++) {
                const int o = 256 * T0 + 512 * k;
                auto at = [&](int d) { return i - d >= 0 && i - d < NS && seq[i - d < 0 ? 0 : i - d < NS ? i - d : 0] == 2 * T0 + 4 * k - 4; };
                if (at(CV_D2)) {
                    cv_store(dq + lc.go + o, xv, yv);
                    if (layer > 19 - 2 * k) __trap();
                }
                if (at(-2)) { ldsm_x4_t(yw, lc.y + o); ldsm_x4_t(yz, lc.y + 3584 + o); }
                if (at(1)) {
#pragma unroll
                    for (int q = 0; q < 4; q++) yw[q] = add2(add2(yw[q], yz[q]), pack2(acc[2 * k + (q >> 1)][2 * (q & 1)], acc[2 * k + (q >> 1)][2 * (q & 1) + 1]));
                    stsm_x4_t(lc.y + o, yw[0], yw[1], yw[2], yw[3]);
                    xv = ldx(smem_u32(Xs) + lc.go + o);
                    __syncwarp();
                    yv = lds4(smem_u32(sm + CV_SM_Y) + c * 8192 + o + usw(lane) * 16);
                    if (layer > 20 - 2 * k) __trap();
                    if (k == 2) CST(6);
                }
            }
        }
    };
    TSTAMP1X(9, 256);
    if (threadIdx.x >= 256) {
        if (threadIdx.x < 288 && elect()) {
            mbar_init(cnt + 48, 1);
            asm volatile("fence.mbarrier_init.release.cluster;" ::: "memory");
            bulk_load(smem_u32(sm + CV_SM_T), tap + d0 * (TAPB / 16), CV_CPB * TAPB, cnt + 48);
            mbar_expect_tx(cnt + 48, CV_CPB * TAPB);
        }
        CV_IDX
        const int wgu = (warp >> 2) & 1, g = lane >> 2, ti = lane & 3;
        CST(1);
        if (warp > 8 && elect()) {
            if (warp < 15) mbar_init(cnt + 8 * (warp - 9), warp == 14 ? 8 : 4);
            else if (layer) prefetch_tmap(&tmOut);
        }
        if (warp < 13 && lane < 17 - (warp == 12)) {
            const int off = warp == 12 ? CV_SM_U : CV_SM_B + (warp == 11 ? BX_7 : (warp - 8) * BX_3), str = warp == 12 ? ULEN * 2 : BX_LEN;
#pragma unroll
            for (int c = 0; c < CV_CPB; c++) *reinterpret_cast<uint4*>(sm + off + c * str + 16 * lane) = make_uint4(0, 0, 0, 0);
        }
        fence_async_smem();
        asm volatile("bar.arrive 3, 512;" ::: "memory");
        asm volatile("bar.sync 1, 256;" ::: "memory");
        TSTAMP1X(10, 256);
        asm volatile("setmaxnreg.inc.sync.aligned.u32 168;");
        const uint32_t Tc = smem_u32(sm + CV_SM_T) + (16 + 128 * (warp & 2) + 8 * (warp & 1) + g - 2 * ti) * 4;
        uint2 fa[8][2], fn[8][2];
        auto near_taps = [&](uint2 (&f)[8][2], int c) {
#pragma unroll
            for (int m = 0; m < 16; m++) f[m >> 1][m & 1] = make_uint2(lds1v(Tc + c * TAPB + 64 * (m >> 1) - 32 * (m & 1)), lds1v(Tc + c * TAPB + 64 * (m >> 1) - 32 * (m & 1) + 512));
        };
        CST(6);
        mbar_wait(cnt + 48, 0);
        TSTAMP1X(11, 256); CST(5);
        near_taps(fa, 3 * wgu);
        near_taps(fn, 2 - wgu);
        const int hc = wgu ? warp & 3 : 4;
        const Lc lc = lane_consts(lane, hc);
        TSTAMP1X(12, 256); CST(0);
        uint32_t ya = smem_u32(sm + CV_SM_Y) + wgu * 8192 + (warp & 2) * 2048 + usw(2 * lane + (warp & 1)) * 16;
        uint64_t db = make_desc(smem_u32(Us + wgu * ULEN + UPADF), 16, 256, 3);
        if (wgu) asm volatile("bar.sync 6, 384;" ::: "memory");
        int c = wgu;
        auto chain = [&](const uint2 (&f)[8][2], auto&& meanwhile) {
            float acc[64];
            asm volatile("bar.sync %0, %1;" ::"r"(c ? 4 + wgu : 2), "r"(c ? 256 : 384) : "memory");
            TSTAMPC(1 + 3 * c);
            if (c < 2) CST(7);
            if (c == 0) fence_async_smem();
            wgmma_fence();
#pragma unroll
            for (int m = 0; m < 8; m++) {
                wgmma_rs128(acc, f[m][0], f[m][1], db - (uint64_t)(2 * m), m);
                if (m == CV_HAND && c < 4) asm volatile("bar.arrive %0, 256;" ::"r"(5 - wgu) : "memory");
            }
            wgmma_commit();
            asm volatile("griddepcontrol.launch_dependents;" ::: "memory");
            TSTAMPC(2 + 3 * c); CST(13 + (c >> 1));
            meanwhile();
            wgmma_wait<0>();
            TSTAMPC(3 + 3 * c); CST(10 + (c >> 1));
            uint32_t w[16];
#pragma unroll
            for (int j = 0; j < 16; j++) w[j] = j ? pack2(acc[4 * j] + acc[4 * j - 2], acc[4 * j + 1] + acc[4 * j - 1]) : pack2(acc[0], acc[1]);
#pragma unroll
            for (int j = 0; j < 16; j += 4) stsm_x4_t(ya + 256 * j, w[j], w[j + 1], w[j + 2], w[j + 3]);
            __syncwarp();
            if (lane == 0) mbar_arrive(cnt + 8 * c);
            c += 2; ya += 16384; db += ULEN / 4;
        };
        const uint32_t e4 = lc.e4, e8 = e4 + 428 - 4 * g;
        uint2 fl[4];
        uint32_t kk;
#pragma unroll 1
        for (;;) {
            if (c != 1) chain(fa, [&] {
                if (c == 3 || warp + c == 12) {
#pragma unroll
                    for (int k = 0; k < 19; k++) (k < 16 ? fn[(k >> 1) & 7][k & 1] : fl[k & 3]) = make_uint2(lds1(k < 10 ? e4 + 32 * k + 16 : e8 + 32 * k - 304), lds1(k < 10 ? e4 + 32 * k : e8 + 32 * k - 320));
                    fl[3] = make_uint2(lds1(lc.en), lds1(lc.en - 32));
                    kk = lds1(smem_u32(sm + CV_SM_T) + TAPB * hc + TAPE + 1672);
                }
            });
            if (c > 4) break;
            if (c == 2) { asm volatile("bar.sync 7, 384;" ::: "memory"); fence_async_smem(); }
            chain(fn, [&] { if (c == 2) near_taps(fa, 4); });
        }
        TSTAMP1X(6, 256); CST(2);
        if (wgu || warp == 8) {
            constexpr int seq[29] = {5, 6, 32, 7, 33, 8, 34, 9, 35, 10, 36, 11, 12, 13, 14, 15, 16, 17, 37, 18, 38, 19, 20, 21, 39, 22, 40, 23, 24};
            uint2 f[20];
#pragma unroll
            for (int k = 0; k < 20; k++) f[k] = k < 16 ? fn[(k >> 1) & 7][k & 1] : fl[k & 3];
            far(Int<10>(), seq, lc, hc, lane, f, kk);
        }
    } else {
        asm volatile("setmaxnreg.dec.sync.aligned.u32 88;");
        CV_IDX
        CST(5);
        const uint4* ppv = piv + tid;
        const float4* psv = sum + tid;
        const uint2* pxv = reinterpret_cast<const uint2*>(x1T + (size_t)d0 * XCP) + (tid >> 4) * 32 + (tid & 15);
        asm volatile("st.shared.u64 [%0], %1;" ::"r"(smem_u32(sm + CV_SM_O) + tid * 16), "l"((uint64_t)ppv ^ (uint64_t)psv ^ (uint64_t)pxv) : "memory");
        const int tc = (0x04302100 >> (4 * warp)) & 7;
        const Lc lc = lane_consts(lane, tc);
        pdl_sync();
        SPAN(3 + 4 * layer, 1);
        TSTAMP(0); CST(0);
        if (tid == 0) TSTAMPC(0);
        if (threadIdx.x == 0) { GSTAMP(g_tim, 15); }
        float4 sv[4];
        uint4 pv;
#pragma unroll
        for (int k = 0; k < 4; k++)
            asm volatile(CV_LD ".v4.f32 {%0,%1,%2,%3}, [%4];" : "=f"(sv[k].x), "=f"(sv[k].y), "=f"(sv[k].z), "=f"(sv[k].w) : "l"(psv + 256 * k) : "memory");
        asm volatile(CV_LD ".v4.u32 {%0,%1,%2,%3}, [%4];" : "=r"(pv.x), "=r"(pv.y), "=r"(pv.z), "=r"(pv.w) : "l"(ppv) : "memory");
        uint2 xe[CV_CPB], xo[CV_CPB];
#pragma unroll
        for (int c = 0; c < CV_NL; c++) {
            asm volatile(CV_LD ".v2.u32 {%0,%1}, [%2];" : "=r"(xe[c].x), "=r"(xe[c].y) : "l"(pxv + c * (XCP / 4)) : "memory");
            asm volatile(CV_LD ".v2.u32 {%0,%1}, [%2];" : "=r"(xo[c].x), "=r"(xo[c].y) : "l"(pxv + c * (XCP / 4) + 16) : "memory");
        }
#define CV_XD 60
#define CV_XW 0
        if (warp == CV_XW) {
            if (elect()) {
                mbar_init(cnt + 56, 1);
                asm volatile("fence.mbarrier_init.release.cluster;" ::: "memory");
                mbar_expect_tx(cnt + 56, CV_CPB * 4096);
                pause(CV_XD);
#pragma unroll
                for (int c = CV_NL; c < CV_CPB + CV_NL; c++) bulk_load(smem_u32(Xs + (c % CV_CPB) * XLEN), x1T + (size_t)(d0 + c % CV_CPB) * XCP, 4096, cnt + 56);
            }
            __syncwarp();
            CST(15);
        }
        uint32_t mw[4];
        float rs[8];
#pragma unroll
        for (int k = 0; k < 4; k++) {
            const uint32_t pw = k == 0 ? pv.x : k == 1 ? pv.y : k == 2 ? pv.z : pv.w;
            uint32_t vr;
            mw[k] = pack2(sv[k].x + __uint_as_float(pw << 16), sv[k].z + __uint_as_float(pw & 0xffff0000u));
            asm("cvt.rn.relu.bf16x2.f32 %0, %1, %2;" : "=r"(vr) : "f"(fmaf(-sv[k].z, sv[k].z, sv[k].w)), "f"(fmaf(-sv[k].x, sv[k].x, sv[k].y)));
            const uint32_t ve = pack2(__uint_as_float(vr << 16) + 1e-5f, __uint_as_float(vr & 0xffff0000u) + 1e-5f);
            const uint32_t sd = pack2(sqrt_apx(__uint_as_float(ve << 16)), sqrt_apx(__uint_as_float(ve & 0xffff0000u)));
            rs[2 * k] = rcp_apx(__uint_as_float(sd << 16)); rs[2 * k + 1] = rcp_apx(__uint_as_float(sd & 0xffff0000u));
        }
        if (rs[0] != 123.f) TSTAMP(13);
        const uint32_t ua = smem_u32(Us) + usw(tid + UPADF / 8) * 16;
        uint32_t uw[CV_CPB][4];
#pragma unroll
        for (int c = 0; c < CV_CPB; c++) {
            if (c == CV_NL) {
                if (warp == CV_XW) { mbar_wait(cnt + 56, 0); CST(7); }
                asm volatile("bar.sync 10, 256;" ::: "memory");
            }
            if (c == 1 || c == 2) {
#pragma unroll
                for (int k = c; k < (c == 1 ? 2 : CV_CPB); k++) {
 const uint4 v = ldx(smem_u32(Xs + k * XLEN) + (tid >> 4) * 256 + (tid & 15) * 8); xe[k] = make_uint2(v.x, v.y); xo[k] = make_uint2(v.z, v.w); }
            }
            const uint32_t e0 = sub2(xe[c].x, mw[0]), e1 = sub2(xe[c].y, mw[1]), o0 = sub2(xo[c].x, mw[2]), o1 = sub2(xo[c].y, mw[3]);
            uw[c][0] = pack2(__uint_as_float(e0 << 16) * rs[0], __uint_as_float(o0 << 16) * rs[4]); uw[c][1] = pack2(__uint_as_float(e0 & 0xffff0000u) * rs[1], __uint_as_float(o0 & 0xffff0000u) * rs[5]);
            uw[c][2] = pack2(__uint_as_float(e1 << 16) * rs[2], __uint_as_float(o1 << 16) * rs[6]); uw[c][3] = pack2(__uint_as_float(e1 & 0xffff0000u) * rs[3], __uint_as_float(o1 & 0xffff0000u) * rs[7]);
            asm volatile("st.shared.v4.u32 [%0], {%1,%2,%3,%4};" ::"r"(ua + c * ULEN * 2), "r"(uw[c][0]), "r"(uw[c][1]), "r"(uw[c][2]), "r"(uw[c][3]) : "memory");
            if (c < 2) {
                if (c == 1) fence_async_smem();
                asm volatile("bar.arrive %0, 384;" ::"r"(2 + 4 * c) : "memory");
                if (layer > 29 - c) __trap();
                CST(11 + c);
            }
        }
        asm volatile("bar.arrive 7, 384;" ::: "memory");
        asm volatile("bar.sync 3, 512;" ::: "memory");
        TSTAMP(1); CST(1);
        {
            auto box = [&](auto c0, auto c1, int chunk, int cb, bool full) {
                const uint32_t ea = smem_u32(Us + cb * ULEN) + usw(chunk + UPADF / 8 + (lane ? 1 : -1)) * 16, bx = smem_u32(sm + CV_SM_B + cb * BX_LEN) + chunk * 16;
                uint32_t lo[CV_CPB][4], hi[CV_CPB][2];
#pragma unroll
                for (int c = c0; c < c1; c++) {
                    lo[c][0] = 0;
#pragma unroll
                    for (int k = 1; k < 4; k++) lo[c][k] = __shfl_up_sync(~0u, uw[c][k], 1);
#pragma unroll
                    for (int k = 0; k < 2; k++) hi[c][k] = __shfl_down_sync(~0u, uw[c][k], 1);
                }
#pragma unroll
                for (int c = c0; c < c1; c++)
                    asm volatile("{\n.reg .pred p, q;\nsetp.eq.s32 p, %7, 0;\nsetp.eq.s32 q, %7, 31;\n@p ld.shared.v4.u32 {%0,%1,%2,%3}, [%6];\n@q ld.shared.v2.u32 {%4,%5}, [%6];\n}"
                                 : "+r"(lo[c][0]), "+r"(lo[c][1]), "+r"(lo[c][2]), "+r"(lo[c][3]), "+r"(hi[c][0]), "+r"(hi[c][1]) : "r"(ea + c * ULEN * 2), "r"(lane) : "memory");
#pragma unroll
                for (int c = c0; c < c1; c++) {
                    const uint32_t e[9] = {lo[c][1], lo[c][2], lo[c][3], uw[c][0], uw[c][1], uw[c][2], uw[c][3], hi[c][0], hi[c][1]};
                    uint32_t o[8], p[8], t[7], b3[5], b5[7];
#pragma unroll
                    for (int i = 0; i < 8; i++) { o[i] = __byte_perm(e[i], e[i + 1], 0x5432); p[i] = add2(e[i], o[i]); }
#pragma unroll
                    for (int i = 0; i < 5; i++) b3[i] = add2(o[i], p[i + 1]);
                    sts4(bx + c * BX_LEN + BX_3 + 160, b3);
#pragma unroll
                    for (int i = 1; i < 7; i++) { t[i] = add2(p[i], p[i + 1]); b5[i] = add2(t[i], e[i + 2]); }
                    sts4(bx + c * BX_LEN + BX_5 + 160, b5 + 2);
                    if (full) {
#pragma unroll
                        for (int i = 1; i < 5; i++) { b3[i] = add2(b3[i], t[i + 2]); t[i] = add2(t[i], b5[i + 2]); }
                        sts4(bx + c * BX_LEN + BX_7 + 272, b3 + 1);
                        sts4(bx + c * BX_LEN + BX_9 + 272, t + 1);
                    }
                }
            };
            auto reload = [&](int c, uint32_t a) { const uint4 v = lds4(a); uw[c][0] = v.x; uw[c][1] = v.y; uw[c][2] = v.z; uw[c][3] = v.w; };
            if (warp >= 6) {
#pragma unroll
                for (int c = 0; c < 3; c++) reload(c, ua - 1024 + (c + 2) * ULEN * 2);
            }
            if (warp >= 4) {
#pragma unroll
                for (int c = 3; c < 5; c++) reload(c, ua - 2048 + c * ULEN * 2);
            }
            box(Int<0>(), Int<3>(), warp < 6 ? tid : tid - 64, warp < 6 ? 0 : 2, warp < 4);
            if (warp >= 4) box(Int<3>(), Int<5>(), tid - 128, 0, true);
            else if (tid >= 128 - CV_CPB) {
                const int c = 127 - tid;
                const uint2 v = *reinterpret_cast<const uint2*>(Us + c * ULEN + UPADF);
                const float s1 = __uint_as_float(v.x << 16), s2 = s1 + __uint_as_float(v.x & 0xffff0000u), s3 = s2 + __uint_as_float(v.y << 16), s4 = s3 + __uint_as_float(v.y & 0xffff0000u);
                unsigned char* bc = sm + CV_SM_B + c * BX_LEN;
                *reinterpret_cast<uint32_t*>(bc + BX_5 + 156) = pack2(s1, s2);
                *reinterpret_cast<uint2*>(bc + BX_7 + 264) = make_uint2(v.x << 16, pack2(s2, s3));
                *reinterpret_cast<uint2*>(bc + BX_9 + 264) = make_uint2(pack2(s1, s2), pack2(s3, s4));
            }
        }
        __syncwarp();
        if (lane == 0) mbar_arrive(cnt + 40);
        TSTAMP(2); CST(2);
        if (layer && blockIdx.x == 0 && tid == 224) g_epoch = ld_epoch();
        __syncwarp();
        if ((0x6e >> warp) & 1) {
            constexpr int seq[16] = {0, 1, 2, 3, 4, 5, 6, 32, 7, 8, 9, 33, 10, 34, 11, 12};
            uint2 f[20];
            mbar_wait(cnt, 0);
            const uint32_t e8 = lc.e4 + 428 - (lane & 28);
#pragma unroll
            for (int k = 0; k < 13; k++) f[k] = make_uint2(lds1(k < 10 ? lc.e4 + 32 * k + 16 : e8 + 32 * k - 304), lds1(k < 10 ? lc.e4 + 32 * k : e8 + 32 * k - 320));
            f[19] = make_uint2(lds1(lc.en), lds1(lc.en - 32));
            far(Int<4>(), seq, lc, tc, lane, f, lds1(smem_u32(sm + CV_SM_T) + TAPB * tc + TAPE + 1672));
        }
    }
    {
        CV_IDX
        if ((0xc91 >> warp) & 1) {
            const int c = __popc(0xc91 & ((1 << warp) - 1));
            uint4 xv[2], yv[2];
#pragma unroll
            for (int k = 0; k < 2; k++) xv[k] = ldx(smem_u32(Xs + c * XLEN) + 512 * k + (lane >> 4) * 256 + (lane & 15) * 8);
            const uint32_t u0 = lds1(smem_u32(Us + c * ULEN) + (lane == 31 ? UPADF * 2 : 0));
            mbar_wait(cnt + 8 * c, 0);
#pragma unroll
            for (int k = 0; k < 2; k++) yv[k] = lds4(smem_u32(sm + CV_SM_Y) + c * 8192 + 512 * k + usw(lane) * 16);
            const uint4 yz = lds4(smem_u32(sm + CV_SM_Y) + c * 8192 + 4096 + usw(lane) * 16);
            const float kk = __uint_as_float(lds1(smem_u32(sm + CV_SM_T) + TAPB * c + TAPE + 1272) << 16);
            yv[1].x = add2(yv[1].x, yz.x); yv[1].y = add2(yv[1].y, yz.y); yv[1].z = add2(yv[1].z, yz.z);
            yv[1].w = pack2(fmaf(kk, __uint_as_float(u0 << 16), __uint_as_float(yv[1].w << 16) + __uint_as_float(yz.w << 16)),
                            fmaf(kk, __uint_as_float(u0 << 16) + __uint_as_float(u0 & 0xffff0000u), __uint_as_float(yv[1].w & 0xffff0000u) + __uint_as_float(yz.w & 0xffff0000u)));
#pragma unroll
            for (int k = 0; k < 2; k++) cv_store(dq + c * XCP * 2 + (lane >> 4) * 256 + (lane & 15) * 8 + 512 * k, xv[k], yv[k]);
        }
        TSTAMP(4); CST(8);
        if (layer == 1) {
            const int rb = (blockIdx.x >> 3) + (warp & 8) * 2, cg = blockIdx.x & 7, ch = (tid >> 3) & 31;
            const bf16* src = dst + (size_t)(cg * 80 + ch) * XCP + rb * 64 + (tid & 7) * 8;
            uint32_t v[3][4];
            __syncthreads();
            pause(warp & 8 ? CV_TD1 : CV_TD0);
            uint32_t todo = (warp & 4) ? 3 : 7;
#pragma unroll 1
            for (int it = 0; it < SPIN_MAX; it++) {
#pragma unroll
                for (int k = 0; k < 3; k++)
                    if (todo >> k & 1)
                        asm volatile("ld.relaxed.gpu.global.v4.u32 {%0,%1,%2,%3}, [%4];" : "=r"(v[k][0]), "=r"(v[k][1]), "=r"(v[k][2]), "=r"(v[k][3]) : "l"(src + k * (32 * XCP)) : "memory");
#pragma unroll
                for (int k = 0; k < 3; k++)
                    if ((todo >> k & 1) && v[k][0] != ~0u && v[k][1] != ~0u && v[k][2] != ~0u && v[k][3] != ~0u) {
                        *reinterpret_cast<uint4*>(sm + (32 * k + ch) * 272 + ((tid & 7) + (warp & 8)) * 16) = make_uint4(v[k][0], v[k][1], v[k][2], v[k][3]);
                        todo ^= 1u << k;
                    }
                if (!todo) break;
                __nanosleep(CV_SLEEP);
            }
            __syncwarp();
            asm volatile("bar.sync %0, 256;" ::"r"(8 + (warp >> 3)) : "memory");
            uint32_t w[12];
#pragma unroll
            for (int k = 0; k < 3; k++) ldsm_x4(&w[4 * k], smem_u32(sm) + min(32 * k + lane, 79) * 272 + warp * 16);
            const uint32_t ot = smem_u32(sm + CV_SM_O) + warp * 1280, oa = ot + (lane & 7) * 160 + (lane >> 3) * 16;
            stsm_x4_t(oa, w[0], w[1], w[2], w[3]);
            stsm_x4_t(oa + 64, w[4], w[5], w[6], w[7]);
            asm volatile("stmatrix.sync.aligned.m8n8.x2.trans.shared.b16 [%0], {%1,%2};" ::"r"(oa + 128), "r"(w[8]), "r"(w[9]) : "memory");
            fence_async_smem();
            __syncwarp();
            if (lane == 0) {
                asm volatile("cp.async.bulk.tensor.3d.global.shared::cta.bulk_group [%0, {%1, %2, %3}], [%4];" ::"l"(&tmOut), "r"(cg * 80), "r"((rb >> 1) * 64 + 8 * (warp & 7)), "r"(rb & 1), "r"(ot) : "memory");
                asm volatile("cp.async.bulk.commit_group;" ::: "memory");
                asm volatile("cp.async.bulk.wait_group.read 0;" ::: "memory");
            }
        }
    }
    TSTAMP(3); CST(9); CST_END;
    GSTAMP(g_tim, 14);
    SPAN(3 + 4 * layer, 3);
}

template <int TA, int TB>
__device__ __forceinline__ void wgmma_n240(float (&d)[120], uint64_t da, uint64_t db, int acc) {
    asm volatile("{\n.reg .pred p;\nsetp.ne.b32 p, %124, 0;\nwgmma.mma_async.sync.aligned.m64n240k16.f32.bf16.bf16 {%0,%1,%2,%3,%4,%5,%6,%7,%8,%9,%10,%11,%12,%13,%14,%15,%16,%17,%18,%19,%20,%21,%22,%23,%24,%25,%26,%27,%28,%29,%30,%31,%32,%33,%34,%35,%36,%37,%38,%39,%40,%41,%42,%43,%44,%45,%46,%47,%48,%49,%50,%51,%52,%53,%54,%55,%56,%57,%58,%59,%60,%61,%62,%63,%64,%65,%66,%67,%68,%69,%70,%71,%72,%73,%74,%75,%76,%77,%78,%79,%80,%81,%82,%83,%84,%85,%86,%87,%88,%89,%90,%91,%92,%93,%94,%95,%96,%97,%98,%99,%100,%101,%102,%103,%104,%105,%106,%107,%108,%109,%110,%111,%112,%113,%114,%115,%116,%117,%118,%119}, %120, %121, p, 1, 1, %122, %123;\n}"
                 : "+f"(d[0]), "+f"(d[1]), "+f"(d[2]), "+f"(d[3]), "+f"(d[4]), "+f"(d[5]), "+f"(d[6]), "+f"(d[7]), "+f"(d[8]), "+f"(d[9]), "+f"(d[10]), "+f"(d[11]), "+f"(d[12]), "+f"(d[13]), "+f"(d[14]), "+f"(d[15]), "+f"(d[16]), "+f"(d[17]), "+f"(d[18]), "+f"(d[19]), "+f"(d[20]), "+f"(d[21]), "+f"(d[22]), "+f"(d[23]), "+f"(d[24]), "+f"(d[25]), "+f"(d[26]), "+f"(d[27]), "+f"(d[28]), "+f"(d[29]), "+f"(d[30]), "+f"(d[31]), "+f"(d[32]), "+f"(d[33]), "+f"(d[34]), "+f"(d[35]), "+f"(d[36]), "+f"(d[37]), "+f"(d[38]), "+f"(d[39]), "+f"(d[40]), "+f"(d[41]), "+f"(d[42]), "+f"(d[43]), "+f"(d[44]), "+f"(d[45]), "+f"(d[46]), "+f"(d[47]), "+f"(d[48]), "+f"(d[49]), "+f"(d[50]), "+f"(d[51]), "+f"(d[52]), "+f"(d[53]), "+f"(d[54]), "+f"(d[55]), "+f"(d[56]), "+f"(d[57]), "+f"(d[58]), "+f"(d[59]), "+f"(d[60]), "+f"(d[61]), "+f"(d[62]), "+f"(d[63]), "+f"(d[64]), "+f"(d[65]), "+f"(d[66]), "+f"(d[67]), "+f"(d[68]), "+f"(d[69]), "+f"(d[70]), "+f"(d[71]), "+f"(d[72]), "+f"(d[73]), "+f"(d[74]), "+f"(d[75]), "+f"(d[76]), "+f"(d[77]), "+f"(d[78]), "+f"(d[79]), "+f"(d[80]), "+f"(d[81]), "+f"(d[82]), "+f"(d[83]), "+f"(d[84]), "+f"(d[85]), "+f"(d[86]), "+f"(d[87]), "+f"(d[88]), "+f"(d[89]), "+f"(d[90]), "+f"(d[91]), "+f"(d[92]), "+f"(d[93]), "+f"(d[94]), "+f"(d[95]), "+f"(d[96]), "+f"(d[97]), "+f"(d[98]), "+f"(d[99]), "+f"(d[100]), "+f"(d[101]), "+f"(d[102]), "+f"(d[103]), "+f"(d[104]), "+f"(d[105]), "+f"(d[106]), "+f"(d[107]), "+f"(d[108]), "+f"(d[109]), "+f"(d[110]), "+f"(d[111]), "+f"(d[112]), "+f"(d[113]), "+f"(d[114]), "+f"(d[115]), "+f"(d[116]), "+f"(d[117]), "+f"(d[118]), "+f"(d[119])
                 : "l"(da), "l"(db), "n"(TA), "n"(TB), "r"(acc));
}

__device__ __forceinline__ void wgmma_n80(float (&d)[40], uint64_t da, uint64_t db, int acc) {
    asm volatile("{\n.reg .pred p;\nsetp.ne.b32 p, %42, 0;\nwgmma.mma_async.sync.aligned.m64n80k16.f32.bf16.bf16 {%0,%1,%2,%3,%4,%5,%6,%7,%8,%9,%10,%11,%12,%13,%14,%15,%16,%17,%18,%19,%20,%21,%22,%23,%24,%25,%26,%27,%28,%29,%30,%31,%32,%33,%34,%35,%36,%37,%38,%39}, %40, %41, p, 1, 1, 0, 1;\n}"
                 : "+f"(d[0]), "+f"(d[1]), "+f"(d[2]), "+f"(d[3]), "+f"(d[4]), "+f"(d[5]), "+f"(d[6]), "+f"(d[7]), "+f"(d[8]), "+f"(d[9]), "+f"(d[10]), "+f"(d[11]), "+f"(d[12]), "+f"(d[13]), "+f"(d[14]), "+f"(d[15]), "+f"(d[16]), "+f"(d[17]), "+f"(d[18]), "+f"(d[19]), "+f"(d[20]), "+f"(d[21]), "+f"(d[22]), "+f"(d[23]), "+f"(d[24]), "+f"(d[25]), "+f"(d[26]), "+f"(d[27]), "+f"(d[28]), "+f"(d[29]), "+f"(d[30]), "+f"(d[31]), "+f"(d[32]), "+f"(d[33]), "+f"(d[34]), "+f"(d[35]), "+f"(d[36]), "+f"(d[37]), "+f"(d[38]), "+f"(d[39])
                 : "l"(da), "l"(db), "r"(acc));
}

constexpr int A1_THREADS = 384;
constexpr int A1_NST = 4;
#define A1_SKEW 8
constexpr int A1_STAGE = 16384 + WQ_STAGE;
constexpr int A1_KVP = 336;
constexpr int A1_SM_KV = 2 * A1_STAGE;
constexpr int A1_SM_END = A1_NST * A1_STAGE;
constexpr int A1_SM_BAR = A1_SM_END + 3072 + 3 * WOB + 64;
constexpr int A1_SM_RS = A1_SM_END + 512;
constexpr int A1_SM_W0 = A1_SM_END + 3072, A1_SM_W3 = A1_SM_END - 3 * WOB, A1_SM_A1 = 2 * WOB, A1_SM_A0 = A1_SM_A1 + 61440;
constexpr int A1_SM_XA = A1_SM_W0 + 2 * WOB, A1_SM_XB = A1_SM_XA + 2048;
constexpr int A1_SMEM = A1_SM_BAR + 512 + 7 * CST_EXTRA / 4;
static_assert(A1_SM_W3 >= A1_SM_KV + 144 * A1_KVP && A1_SM_W3 % 512 == 0 && A1_SM_A1 % 1024 == 0 && A1_SM_A0 <= A1_SM_KV && A1_SM_A0 + 61440 <= A1_SM_W3 && A1_SMEM <= 232448 && 11 * 4096 <= A1_STAGE, "layout");
__device__ __forceinline__ constexpr uint32_t wo_off(int h) { return h * WOB + (h < 3 ? A1_SM_W0 : h < 6 ? A1_SM_W3 - 3 * WOB : -6 * WOB); }
#define A1_FRED "red.relaxed.gpu.global.add.u32"
#define A1_FLD "ld.relaxed.gpu.global.u32"
#define ST_SLEEP 20
#define ST_SLEEP0 300
#define A1_P0 2
#define A1_PW (kb - 2)
#define A1_FSPIN SPIN_MAX
#define A1_FSLEEP 40
#define YT_LAYER 1
#define WOT 11
#define A1_P1 550
#define A1_P2 300
#define A1_WOAT 6

template <int L>
__device__ __forceinline__ void a1_mainloop(float (&acc)[120], uint32_t sbase, uint32_t bars, int wg, int tile) {
    constexpr int layer = L; (void)layer;
    const uint64_t da0 = L ? make_desc(sbase + wg * 8192, 8192, 1024, 1) : make_desc(sbase + wg * 8192, 16, 1024, 1), db0 = make_desc(sbase + 16384, 1024, 256, 3);
#pragma unroll 1
    for (int t = 0;; t++) {
        const int st = t % A1_NST;
        mbar_wait(bars + 8 * st, (t / A1_NST) & 1);
        if (t == A1_SKEW && wg == 0) mbar_wait(bars + 160, 0);
        TSTAMP3(1 + t);
        if (t == 0) CSA(0);
        wgmma_fence();
#pragma unroll
        for (int kk = 0; kk < 4; kk++) wgmma_n240<L, 1>(acc, da0 + (uint32_t)(st * (A1_STAGE / 16) + kk * (L ? 128 : 2)), db0 + (uint32_t)(st * (A1_STAGE / 16) + (kk >> 1) * (WQ_STAGE / 32) + (kk & 1) * 32), kk ? 1 : t);
        wgmma_commit();
        if (t == 9) break;
        if (t == A1_SKEW - 1 && wg == 0) wgmma_wait<0>(); else wgmma_wait<1>();
        if (t > 0 && (threadIdx.x & 127) == 0) {
            if (t != A1_SKEW || wg) mbar_arrive(bars + 8 * (A1_NST + (t - 1) % A1_NST));
            if (t == A1_SKEW - 1 && wg == 0) mbar_arrive(bars + 8 * (A1_NST + t % A1_NST));
        }
    }
}

template <bool MAP>
__global__ void __launch_bounds__(A1_THREADS, 1) a1_kernel(const __grid_constant__ Par in, const __grid_constant__ CUtensorMap tmX, const __grid_constant__ CUtensorMap tmR,
                                                           const __grid_constant__ CUtensorMap tmX1, const __grid_constant__ KgMaps tmW, const __grid_constant__ TileTab tab) {
#define layer in.layer
    const unsigned char* const wo = reinterpret_cast<const unsigned char*>(in.wop);
    float2* const rsum = reinterpret_cast<float2*>(in.sum);
    uint4* const of = in.of;
    extern __shared__ __align__(1024) unsigned char stg[];
    const uint32_t sbase = smem_u32(stg);
    const uint32_t bars = sbase + A1_SM_BAR;
    const uint32_t bar_stat = bars + 64, bar_kv = bars + 72, bar_rd = bars + 168;
    const uint32_t bar_wo = bars + 208, bar_done = bars + 216, bar_pv = bars + 224, bar_kvf = bars + 232, bar_f2 = bars + 248, bar_e2 = bars + 384, que = bars + 448;
    const int tid = threadIdx.x;
    CSK(0);
    const int w = __shfl_sync(~0u, tid >> 5, 0), wg = w >> 2;
    uint32_t smid;
    asm volatile("mov.u32 %0, %smid;" : "=r"(smid));
    const uint4 tv = tab.e[(MAP ? smid : blockIdx.x) + (tid & (smid >> 12))];
    const uint64_t pa = reinterpret_cast<const uint64_t*>(&in)[tid & (smid >> 12)], pb = reinterpret_cast<const uint64_t*>(&in)[6 + (tid & (smid >> 12))];
    const bool one = elect();
    uint32_t tz;
    const unsigned char* wq;
    auto entry = [&] { tz = __shfl_sync(~0u, tv.z, 0); wq = (const unsigned char*)(((uint64_t)__shfl_sync(~0u, tv.y, 0) << 32) | __shfl_sync(~0u, tv.x, 0)); };
    auto issue_w = [&](unsigned it) { bulk_load(sbase + (it % A1_NST) * A1_STAGE + 16384, wq + it * WQ_STAGE, WQ_STAGE, bars + 8 * (it % A1_NST)); };
    auto issue_x = [&](unsigned it, int kb) {
        asm volatile("cp.async.bulk.tensor.5d.shared::cluster.global.mbarrier::complete_tx::bytes [%0], [%1, {%3, %3, %3, %4, %5}], [%2];"
                     ::"r"(sbase + (it % A1_NST) * A1_STAGE), "l"(&tmX), "r"(bars + 8 * (it % A1_NST)), "r"(0), "r"(tz & 15), "r"(kb) : "memory");
    };
    auto first_x = [&] {
        issue_x(0, (tz >> 16) & 7); issue_x(1, ((tz >> 16) & 7) + 1);
    };
    auto expect = [&] {
#pragma unroll
        for (int i = 0; i < A1_NST; i++) mbar_expect_tx(bars + 8 * i, A1_STAGE);
    };
    if (w == 8) {
        if (one) {
            prefetch_tmap(&tmX); prefetch_tmap(&tmW.q);
#pragma unroll
            for (int i = 0; i < A1_NST; i++) mbar_init(bars + 8 * i, 1);
            asm volatile("fence.mbarrier_init.release.cluster;" ::: "memory");
        }
        __syncwarp();
        asm volatile("bar.arrive 0, 384;" ::: "memory");
        if (smid >> 12) __trap();
        entry();
        if ((tz & 0x80000010u) == 16) {
            if (one) {
                issue_w(0);
                asm volatile("griddepcontrol.wait;" ::: "memory");
                issue_x(0, (tz >> 16) & 7);
                expect();
                pause(A1_P1);
                issue_w(1);
                issue_x(1, ((tz >> 16) & 7) + 1);
                asm volatile("griddepcontrol.launch_dependents;" ::: "memory");
            }
#pragma unroll
            for (int kb = 2; kb < A1_NST; kb++) {
                __syncwarp();
                mbar_wait(bars + 8 * (kb - 2), 0);
                if (kb == 2) pause(A1_P2);
                if (one) { issue_x(kb, ((tz >> 16) & 7) + kb); issue_w(kb); }
                CSK(6 + kb);
            }
        }
        __syncwarp();
        if (!(tz & 16) && blockIdx.x < 128) kgen_first(in, tmW, sbase + A1_SM_W0, bars - 24, one);
        __syncwarp();
    }
    if (w > 8) CSK(8);
    const bool gen = w != 8 && in.logA && blockIdx.x < 128;
    KgPar kp;
    const int w11 = w < 8 ? 2 * (w & 3) + (w >> 2) : w - 1;
    if (gen) kgen_load(in, reinterpret_cast<const bf16*>(pa), w11, kp);
    if (w > 8) CSK(9);
    if (w == 8) {
        const int tile = tz >> 24, mb = tz & 15, hg = (tz >> 8) & 7, kb0 = (tz >> 16) & 7;
        const unsigned l1 = (tz >> 4) & 1;
        if (__builtin_expect(!l1, 0)) {
            CSK(1);
            const uint32_t ep = ld_epoch();
            if (one) {
                kgen_side(in, sbase + A1_SM_W0, bars - 24);
                if (tile < 128) { first_x(); expect(); }
                asm volatile("cp.async.bulk.wait_group 0;" ::: "memory");
            }
            __syncwarp();
            asm volatile("bar.arrive 10, 96;" ::: "memory");
            CSK(6);
            if (tile < 128) {
                await_all(96 + 32 * hg, ep * 15);
                if (one) issue_w(0);
                __syncwarp();
                pause(800);
                if (one) issue_w(1);
                __syncwarp();
                mbar_wait(bars, 0);
                pause(400);
                if (one) { issue_x(2, kb0 + 2); issue_w(2); }
            }
            CSK(7);
            asm volatile("bar.sync 3, 384;" ::: "memory");
            if (tile < 128 && one) {
                fence_async_smem();
                issue_x(3, kb0 + 3); issue_w(3);
                mbar_expect_tx(bars + 240, 20480);
                bulk_load(sbase + A1_SM_W0, in.x + (size_t)(mb * 128 + hg * 16) * DM, 20480, bars + 240);
            }
            __syncwarp();
            CSK(9);
        } else asm volatile("bar.sync 3, 64;" ::: "memory");
        if (tile < 128 && elect()) {
#pragma unroll 1
            for (unsigned kb = A1_NST; kb < 10; kb++) {
                mbar_wait(bars + 8 * (A1_NST + kb % A1_NST), ((kb / A1_NST) - 1) & 1);
                if (l1 && kb < 9) mbar_wait(bar_rd + 8 * (kb - A1_NST), 0);
                mbar_expect_tx(bars + 8 * (kb % A1_NST), A1_STAGE);
                issue_x(kb, kb < 5 ? kb + kb0 : kb - kb0); issue_w(kb);
                if (kb == (l1 ? A1_WOAT : 9)) {
                    if (!l1) { mbar_wait(bar_stat, 0); asm volatile("fence.proxy.async.global;" ::: "memory"); }
                    mbar_expect_tx(bar_wo, 8 * WOB);
                    bulk_load(sbase + A1_SM_W0, wo + hg * 8 * WOB, 2 * WOB, bar_wo);
                }
            }
            mbar_wait(bars + 8 * (A1_NST + 3), 1);
            bulk_load(sbase + A1_SM_W3, wo + (hg * 8 + 3) * WOB, 3 * WOB, bar_wo);
        }
        CSA(4); CSA_END;
        return;
    }
    {
        if (w < 8 && one) {
#pragma unroll 1
            for (uint32_t c = (w & 4 ? w & 2 ? 0x1111112'01111111ull : 0x1111111'01111184ull : w & 2 ? 0x3122222'01111111ull : 0x1111132'02220000ull) >> (32 * (w & 1)), b = bars + 56 * w; c; c >>= 4, b += 8)
                if (c & 15) mbar_init(b, c & 15);
            asm volatile("fence.mbarrier_init.release.cluster;" ::: "memory");
        }
        __syncwarp();
        asm volatile("bar.sync 0, 384;" ::: "memory");
        if (layer) {
            if (w == 9) asm volatile("bar.arrive 3, 64;" ::: "memory");
        } else {
            if (gen) { SPAN(0, 0); SPAN(0, 1); kgen_tables(in, reinterpret_cast<uint4*>(stg + 3 * A1_STAGE), w11, kp); }
            else if (w != 11 && w11 > 1) asm volatile("bar.arrive 9, 352;" ::: "memory");
            __syncwarp();
            if (w11 < 2) {
                asm volatile("bar.sync 10, 96;" ::: "memory");
                kgen_sums(in, sbase + A1_SM_W0, w11);
                __syncwarp();
                asm volatile("bar.arrive 9, 352;" ::: "memory");
                CSK(1);
            }
            if (w == 9) asm volatile("bar.sync 3, 384;" ::: "memory"); else asm volatile("bar.arrive 3, 384;" ::: "memory");
        }
    }
    tz = __shfl_sync(~0u, tv.z + (uint32_t)(pb >> 32), 0);
    const int tile = tz >> 24, mb = tz & 15, hg = (tz >> 8) & 7;
    float2* rst = reinterpret_cast<float2*>(stg + A1_SM_RS) + 8;
    if (wg == 2) {
        if (w == 11 && layer == 0) {
            asm volatile("bar.sync 9, 352;" ::: "memory");
            CSK(5);
            if (one) publish(64);
            __syncwarp();
            CSK(6);
        }
        if (tile >= 128) { sm_idle(layer); return; }
        if (w == 10) {
            if (one) { prefetch_tmap(&tmR); prefetch_tmap(&tmX1); }
            uint32_t ns;
            asm volatile("mov.u32 %0, %nsmid;" : "=r"(ns));
            if (MAP && ns != 132) __trap();
        }
        __syncwarp();
        if (w == 9) {
            if (layer && one) {
                mbar_expect_tx(bar_stat, 3840);
                bulk_load(sbase + A1_SM_XB, g_xb + tile * 240, 3840, bar_stat);
            }
            __syncwarp();
#pragma unroll 1
            for (int it = 0; it < 4096 * layer; it++) {
                uint32_t ok;
                asm volatile("{\n.reg .pred p;\nmbarrier.try_wait.parity.shared::cta.b64 p, [%1], %2;\nselp.b32 %0, 1, 0, p;\n}" : "=r"(ok) : "r"(bars + 8), "n"(0) : "memory");
                if (__any_sync(~0u, ok)) break;
            }
            uint4* pre = of + (mb * 8 + hg) * 1280 + (tid - 288);
#pragma unroll 1
            for (int k = 0; k < 5 + 5 * layer; k++) {
#pragma unroll
                for (int i = 0; i < 8; i++) asm volatile("st.global.v4.u32 [%0], {%1,%1,%1,%1};" ::"l"(pre + 32 * i), "r"(~0u) : "memory");
                pre += k < 5 ? 256 : XCP / 8;
                if (layer) pause(400);
                if (k == 4) {
                    CSA(2);
                    asm volatile("fence.acq_rel.gpu;" ::: "memory");
                    asm volatile("fence.proxy.async.global;" ::: "memory");
                    __syncwarp();
                    if (tid == 288) mbar_arrive(bar_done);
                    CSA(3);
                    pre = reinterpret_cast<uint4*>(g_yT) + tile * (5 * XCP / 8) + (tid - 288);
                }
            }
            if (layer == 0) {
                asm volatile("griddepcontrol.launch_dependents;" ::: "memory");
                await_all(64, ld_epoch() * gridDim.x);
                CSA(5);
                float4 a[2] = {};
#pragma unroll
                for (int k = 0; k < 10; k++)
#pragma unroll
                    for (int h = 0; h < 2; h++) {
                        const int c4 = min(tid - 288 + 32 * h, 59);
                        const float4 v = __ldcg(reinterpret_cast<const float4*>(g_csp + (k / 5) * 9600 + (k % 5) * 640 + hg * 80) + c4 + (c4 / 20) * 780);
                        a[h].x += v.x; a[h].y += v.y; a[h].z += v.z; a[h].w += v.w;
                    }
#pragma unroll
                for (int h = 0; h < 2; h++)
#pragma unroll
                    for (int k = 0; k < 4; k++) {
                        const float c = 0.5f * (k == 0 ? a[h].x : k == 1 ? a[h].y : k == 2 ? a[h].z : a[h].w), c1 = c - rbf(c), c2 = c1 - rbf(c1);
                        *reinterpret_cast<uint4*>(stg + A1_SM_XB + (4 * min(tid - 288 + 32 * h, 59) + k) * 16) = make_uint4(pack2(c, c1), pack2(c2, 0.f), 0u, 0u);
                    }
                fence_async_smem();
                __syncwarp();
                if (one) {
                    bulk_store(g_xb + tile * 240, sbase + A1_SM_XB, 3840);
                    asm volatile("cp.async.bulk.commit_group;" ::: "memory");
                    asm volatile("cp.async.bulk.wait_group.read 0;" ::: "memory");
                    mbar_arrive(bar_stat);
                }
                __syncwarp();
                CSA(1);
            }
            TSTAMP1T(9, 288);
        } else {
            const int j = tid - 320;
            const uint32_t tag = ld_epoch();
            if (tid == 352) sm_started(layer);
            const int ch = j & 7, kg = (j >> 3) & 3;
            const unsigned char* src = stg + (layer ? (j >> 5) * 8192 + (hg & 3) * 2048 : A1_SM_W0 + (j >> 2) * 1280);
            const int of0 = layer ? kg * 128 + ((ch ^ kg) << 4) : (j & 7) << 4, ofx = layer ? 576 : 64, ofy = layer ? 1024 : 128;
            float s[8], q[8], p0[8];
#pragma unroll
            for (int i = 0; i < 8; i++) { s[i] = 0.f; q[i] = 0.f; }
#pragma unroll 1
            for (int it = 0; it < 5; it++) {
                uint4 v[4];
                mbar_wait(layer ? bars + 8 * (it % A1_NST) : bars + 240, layer * it / A1_NST);
#pragma unroll
                for (int k = 0; k < 4; k++) v[k] = *reinterpret_cast<const uint4*>(src + (layer ? (it % A1_NST) * A1_STAGE : it * 256) + (k & 1 ? of0 ^ ofx : of0) + (k >> 1) * ofy);
                if (it == 0) {
                    const uint4 pv = *reinterpret_cast<const uint4*>(src + (layer ? ch << 4 : 0));
                    const uint32_t w[4] = {pv.x, pv.y, pv.z, pv.w};
#pragma unroll
                    for (int i = 0; i < 4; i++) { p0[2 * i] = __uint_as_float((layer ? w[i] : w[0]) << 16); p0[2 * i + 1] = __uint_as_float(layer ? w[i] & 0xffff0000u : w[0] << 16); }
                }
                asm volatile("" :: "r"(v[0].x), "r"(v[1].x), "r"(v[2].x), "r"(v[3].x), "f"(p0[0]) : "memory");
                __syncwarp();
                if ((tid & 31) == 0) mbar_arrive(bar_rd + 8 * it);
#pragma unroll
                for (int k = 0; k < 4; k++) {
                    const uint32_t w[4] = {v[k].x, v[k].y, v[k].z, v[k].w};
#pragma unroll
                    for (int i = 0; i < 4; i++) {
                        const float a = __uint_as_float(w[i] << 16) - p0[2 * i], b = __uint_as_float(w[i] & 0xffff0000u) - p0[2 * i + 1];
                        s[2 * i] += a; s[2 * i + 1] += b; q[2 * i] = fmaf(a, a, q[2 * i]); q[2 * i + 1] = fmaf(b, b, q[2 * i + 1]);
                    }
                }
            }
            float o[4];
            int row;
            if (layer == 0) {
                float s0 = ((s[0] + s[1]) + (s[2] + s[3])) + ((s[4] + s[5]) + (s[6] + s[7])), q0 = ((q[0] + q[1]) + (q[2] + q[3])) + ((q[4] + q[5]) + (q[6] + q[7]));
#pragma unroll
                for (int o = 1; o <= 2; o <<= 1) { s0 += __shfl_xor_sync(~0u, s0, o); q0 += __shfl_xor_sync(~0u, q0, o); }
                if ((j & 3) == 0) {
                    const float d = s0 * (1.0f / DM);
                    const uint32_t ms = pack2(p0[0] + d, sqrt_apx(rbf(rbf(fmaxf(fmaf(-d, d, q0 * (1.0f / DM)), 0.f)) + 1e-5f)));
                    asm volatile("st.global.cg.u64 [%0], %1;" ::"l"(g_rstat + mb * 128 + (j & 4) * 16 + hg * 8 + (j >> 3)), "l"(tagw(ms, tag)) : "memory");
                    g_piv[mb * 128 + hg * 16 + ((j >> 2) & 8) + (j & 4) + ((j >> 3) & 3)] = __ushort_as_bfloat16((unsigned short)ms);
                }
                ulonglong2 v;
#pragma unroll 1
                for (int it = 0; it < SPIN_MAX; it++) {
                    v = ld_tag2(reinterpret_cast<const ulonglong2*>(g_rstat + mb * 128) + j);
                    if (__all_sync(~0u, tag_ok(v, tag))) break;
                    __nanosleep(100);
                }
                o[0] = __uint_as_float((uint32_t)v.x << 16); o[1] = rcp_apx(__uint_as_float((uint32_t)v.x & 0xffff0000u));
                o[2] = __uint_as_float((uint32_t)v.y << 16); o[3] = rcp_apx(__uint_as_float((uint32_t)v.y & 0xffff0000u));
                row = 2 * j;
            } else {
#pragma unroll
                for (int i = 0; i < 4; i++) {
                    const bool up = kg & 2;
                    const float ss = __shfl_xor_sync(~0u, up ? s[i] : s[i + 4], 16), qq = __shfl_xor_sync(~0u, up ? q[i] : q[i + 4], 16);
                    s[i] = (up ? s[i + 4] : s[i]) + ss; q[i] = (up ? q[i + 4] : q[i]) + qq; p0[i] = up ? p0[i + 4] : p0[i];
                }
#pragma unroll
                for (int i = 0; i < 2; i++) {
                    const bool up = kg & 1;
                    const float ss = __shfl_xor_sync(~0u, up ? s[i] : s[i + 2], 8), qq = __shfl_xor_sync(~0u, up ? q[i] : q[i + 2], 8);
                    s[i] = (up ? s[i + 2] : s[i]) + ss; q[i] = (up ? q[i + 2] : q[i]) + qq; p0[i] = up ? p0[i + 2] : p0[i];
                }
                uint4* gp = g_halo + 86016 + mb * 512 + j;
                const float d0 = s[0] * (1.0f / 80.0f), d1 = s[1] * (1.0f / 80.0f);
                asm volatile("st.relaxed.gpu.global.v4.f32 [%0], {%1,%2,%3,%4};" ::"l"(gp + hg * 64), "f"(p0[0] + d0), "f"(fmaxf(fmaf(-d0, s[0], q[0]), 0.f)), "f"(p0[1] + d1), "f"(fmaxf(fmaf(-d1, s[1], q[1]), 0.f)) : "memory");
                __nanosleep(ST_SLEEP0);
                uint32_t pw[8][4], todo = 0xff;
#pragma unroll 1
                for (int it = 0; it < SPIN_MAX; it++) {
#pragma unroll
                    for (int k = 0; k < 8; k++)
                        if (todo >> k & 1) asm volatile("ld.relaxed.gpu.global.v4.u32 {%0,%1,%2,%3}, [%4];" : "=r"(pw[k][0]), "=r"(pw[k][1]), "=r"(pw[k][2]), "=r"(pw[k][3]) : "l"(gp + k * 64) : "memory");
#pragma unroll
                    for (int k = 0; k < 8; k++)
                        if (__all_sync(~0u, pw[k][0] != ~0u && pw[k][1] != ~0u && pw[k][2] != ~0u && pw[k][3] != ~0u)) todo &= ~(1u << k);
                    if (!todo) break;
                    __nanosleep(ST_SLEEP);
                }
#pragma unroll
                for (int r = 0; r < 2; r++) {
                    float mean = 0.f, m2 = 0.f;
#pragma unroll
                    for (int k = 0; k < 8; k++) mean += __uint_as_float(pw[k][2 * r]);
                    mean *= 0.125f;
#pragma unroll
                    for (int k = 0; k < 8; k++) {
                        const float dm = __uint_as_float(pw[k][2 * r]) - mean;
                        m2 += fmaf(80.0f * dm, dm, __uint_as_float(pw[k][2 * r + 1]));
                    }
                    o[2 * r] = rbf(mean);
                    o[2 * r + 1] = rcp_apx(rbf(sqrt_apx(rbf(rbf(m2 * (1.0f / DM)) + 1e-5f))));
                }
                row = (j >> 5) * 64 + (j & 7) * 8 + ((j >> 3) & 3) * 2;
                if (hg == 0) *reinterpret_cast<uint32_t*>(g_piv + SEQ + mb * 128 + 2 * (row & 60) + 4 * (row >> 6) + (row & 3)) = __byte_perm(__float_as_uint(o[0]), __float_as_uint(o[2]), 0x7632);
            }
#pragma unroll
            for (int r = 0; r < 2; r++)
                *reinterpret_cast<uint4*>(stg + A1_SM_XA + (row + r) * 16) = make_uint4(__byte_perm(__float_as_uint(-o[2 * r]), 0, 0x3232), __float_as_uint(-o[2 * r]) >> 16, 0u, 0u);
            *reinterpret_cast<float4*>(rst + row + (row >> 6) * 8) = make_float4(o[0], o[1], o[2], o[3]);
            fence_async_smem();
            TSTAMP1T(7, 320); CSA(1);
            if (tid == 320) DBGC(44);
            __syncwarp();
            if ((tid & 31) == 0) mbar_arrive(bar_stat);
        }
        CSA(4); CSA_END;
        if (tid == 320) DBGCAL(0);
        __syncwarp();
        if (w == WOT) {
            mbar_wait(bars + 416, 0);
            mbar_wait(bar_done, 0);
            if (one) {
                bulk_load(sbase, wo + (hg * 8 + 6) * WOB, 2 * WOB, bar_wo);
                bulk_load(sbase + A1_SM_W0 + 2 * WOB, wo + (hg * 8 + 2) * WOB, WOB, bar_wo);
            }
            __syncwarp();
        }
#define FWA 11
#define FWB 10
        if (w == FWA || w == FWB) {
            const int cw = w == FWB;
            const uint32_t* fl = reinterpret_cast<const uint32_t*>(rsum + 2 * SEQ) + (((layer * 16 + mb) * 2 + cw) * 8 + (tid & 7)) * FSTR;
            const unsigned char* src = reinterpret_cast<const unsigned char*>(of) + mb * 163840 + cw * 10240 + (tid & 7) * 20480;
            const uint32_t sl = sbase + (cw ? A1_SM_A1 : A1_SM_A0);
            mbar_wait(cw ? bar_done : bar_kvf, 0);
            if (one) {
                mbar_expect_tx(bar_f2 + 64 * cw + 64, 10240);
                tma_load_3d(sl + 51200, &tmR, layer ? 0 : hg * 80, layer ? hg * 80 : mb * 64, layer ? mb * 2 + cw : cw, bar_f2 + 64 * cw + 64);
            }
            __syncwarp();
            uint32_t pend = 0xffu & ~(1u << hg), v = 0;
            const uint32_t bo = wo_off((tid & 7) + ((tid & 7) < hg)) >> 4, lt = (1u << (tid & 31)) - 1;
#pragma unroll 1
            for (int it = 0; pend && it < 2 * SPIN_MAX; it++) {
                if (v != 4 && (pend >> (tid & 31) & 1)) asm volatile(A1_FLD " %0, [%1];" : "=r"(v) : "l"(fl) : "memory");
                uint32_t fr;
                asm volatile("{\n.reg .pred p;\nmbarrier.test_wait.parity.shared::cta.b64 p, [%1], 0;\nselp.b32 %0, 1, 0, p;\n}" : "=r"(fr) : "r"(bar_e2 + 16 * cw + (tid & 1) * 8) : "memory");
                fr = __ballot_sync(~0u, fr);
                uint32_t m = __ballot_sync(~0u, v == 4 || it >= A1_FSPIN) & pend;
                const int q = 8 - __popc(pend) + __popc(m & lt);
                m &= __ballot_sync(~0u, q < ((fr & 2) ? 8 : (fr & 1) ? 7 : 5));
                pend ^= m;
                if (m >> (tid & 31) & 1) DBGC(12 + cw * 8 + (tid & 7));
                if (!m) __nanosleep(A1_FSLEEP);
                if (m >> (tid & 31) & 1) {
                    bulk_load(q == 7 && !cw ? sbase + A1_SM_W0 : sl + (q < 6 ? q : q - 6) * 10240, src, 10240, bar_f2 + 64 * cw + 8 * q);
                    asm volatile("st.shared.u32 [%0], %1;" ::"r"(que + 32 * cw + 4 * q), "r"(bo) : "memory");
                    mbar_expect_tx(bar_f2 + 64 * cw + 8 * q, 10240);
                    DBGC(44 + cw * 8 + q);
                }
                __syncwarp();
            }
        }
    } else if (tile < 128) {
        SPAN(1 + 4 * layer, 0);
        constexpr int on = 1;
        float acc[120];
        const int lane = tid & 31, warp = w & 7, g = lane >> 2, t = lane & 3;
        if (on) {
            SPAN(1 + 4 * layer, 1);
            TSTAMP1(0);
            if (threadIdx.x == 0) { GSTAMP(g_tim1, 15); }
            TSTAMP3(0);
            if (tid == 0) TSTAMP2(0);
            TSTAMP4(0);
            if (tid == 0) DBGC(60);
            if (layer == 0) a1_mainloop<0>(acc, sbase, bars, wg, tile); else a1_mainloop<1>(acc, sbase, bars, wg, tile);
            uint32_t ok;
            asm volatile("{\n.reg .pred p;\nmbarrier.test_wait.parity.shared::cta.b64 p, [%1], 0;\nselp.b32 %0, 1, 0, p;\n}" : "=r"(ok) : "r"(bar_stat) : "memory");
            if (tid == 128 && !ok) mbar_arrive(bars + 160);
            __syncwarp();
            mbar_wait(bar_stat, 0);
            wgmma_fence();
            wgmma_n240<0, 0>(acc, make_desc(sbase + A1_SM_XA + wg * 1024, 0, 128, 0), make_desc(sbase + A1_SM_XB, 0, 128, 0), 1);
            wgmma_commit();
            if (tid == 128 && ok) mbar_arrive(bars + 160);
            mbar_wait(bars + 8 * (A1_NST + 3), 1);
        }
        uint4* hp = g_halo + (((layer * 16 + mb - ((warp & 3) != 3)) * 8 + hg) * 2 + wg) * 168 + lane;
        float* hr = reinterpret_cast<float*>(hp - lane + 160) + ((warp & 3) == 3 ? g : 2 * t);
        asm volatile("" : "+l"(hp), "+l"(hr));
        const float2* rw = rst + 16 * warp + 8 * wg;
        const float rb0 = rw[g + 8].y, ra = rw[g].y * 0.22360679774997896f, rb = rb0 * 0.22360679774997896f;
        wgmma_wait<0>();
        if ((tid & 127) == 0) mbar_arrive(bar_done);
        TSTAMP1(2); CSA(1);
        TSTAMP1T(13, 224);
        if ((tid & 127) == 0) DBGC(62 - wg);
        uint32_t f[2][30];
#pragma unroll
        for (int j = 10; j < 30; j++) f[1][j] = pack2(acc[4 * j + 2], acc[4 * j + 3]);
        if ((warp & 3) == 3) {
#pragma unroll
            for (int j = 0; j < 20; j += 4) {
                const int a = j < 12 ? 10 + j : 8 + j, b = j == 8 ? 28 : a + 2;
                asm volatile("st.relaxed.gpu.global.v4.u32 [%0], {%1,%2,%3,%4};" ::"l"(hp + 8 * j), "r"(f[1][a]), "r"(f[1][a + 1]), "r"(f[1][b]), "r"(f[1][b + 1]) : "memory");
            }
            if (t == 0) asm volatile("st.relaxed.gpu.global.f32 [%0], %1;" ::"l"(hr), "f"(rb0) : "memory");
        }
        TSTAMP1T(12, 224);
        const uint32_t kvw = sbase + A1_SM_KV + (16 * warp + 8 * wg) * A1_KVP;
        const uint32_t mrow = kvw + (lane & 7) * A1_KVP + (lane >> 3) * 16;
#pragma unroll
        for (int j = 0; j < 20; j += 4) {
            const int a = j < 12 ? 10 + j : 8 + j, b = j == 8 ? 28 : a + 2;
            stsm_x4(mrow + 16 * A1_KVP + 16 * (a - 10) + (j == 8 ? (lane & 16) * 8 : 0), f[1][a], f[1][a + 1], f[1][b], f[1][b + 1]);
        }
        __syncwarp();
        if (lane == 0 && (warp & 3) != 3) mbar_arrive(bar_kv + 8 * (warp + 1));
#pragma unroll
        for (int j = 0; j < 30; j++) f[0][j] = pack2(acc[4 * j], acc[4 * j + 1]);
        stsm_x4(mrow + 8 * A1_KVP + 160, f[0][20], f[0][21], f[0][22], f[0][23]);
        stsm_x4(mrow + 8 * A1_KVP + 224, f[0][24], f[0][25], f[0][26], f[0][27]);
        asm volatile("stmatrix.sync.aligned.m8n8.x2.shared.b16 [%0], {%1,%2};" ::"r"(mrow + 8 * A1_KVP + 288), "r"(f[0][28]), "r"(f[0][29]) : "memory");
#pragma unroll
        for (int j = 0; j < 10; j++) f[1][j] = pack2(acc[4 * j + 2], acc[4 * j + 3]);
        __syncwarp();
        uint32_t vb[10][2], hv[24] = {}, *kp = hv, *vp = hv + 12;
#pragma unroll
        for (int j = 0; j < 10; j += 2) ldsm_x4_t(&vb[j][0], kvw + (8 + (lane & 15)) * A1_KVP + 160 + (lane >> 4) * 16 + 16 * j);
        const bool up0 = 2 * t > g, up1 = 2 * t + 1 > g, edge = (mb | (warp & 3)) == 0;
        float rk[4];
        auto above = [&]() {
            mbar_wait(bar_kv + 8 * warp, 0);
#pragma unroll
            for (int j = 0; j < 12; j += 4) ldsm_x4(&kp[j], mrow + 16 * j);
            rk[0] = rw[2 * t - (up0 ? 8 : 0)].y; rk[1] = rw[2 * t + 1 - (up1 ? 8 : 0)].y;
#pragma unroll
            for (int j = 0; j < 8; j += 4) ldsm_x4_t(&vp[j], mrow + 160 + 16 * j);
            asm volatile("ldmatrix.sync.aligned.m8n8.x2.trans.shared.b16 {%0,%1}, [%2];" : "=r"(vp[8]), "=r"(vp[9]) : "r"(mrow + 288) : "memory");
            __syncwarp();
            if (lane == 0) mbar_arrive(bar_kvf);
        };
        auto ask = [&]() {
            if (mb > 0) {
#pragma unroll
                for (int k = 0; k < 20; k += 4)
                    asm volatile("ld.relaxed.gpu.global.v4.u32 {%0,%1,%2,%3}, [%4];" : "=r"(hv[k]), "=r"(hv[k + 1]), "=r"(hv[k + 2]), "=r"(hv[k + 3]) : "l"(hp + 8 * k) : "memory");
                asm volatile("ld.relaxed.gpu.global.v2.u32 {%0,%1}, [%2];" : "=r"(hv[20]), "=r"(hv[21]) : "l"(hr) : "memory");
            }
        };
        auto halo = [&]() {
            if (lane == 0) mbar_arrive(bar_kvf);
            rk[0] = rw[2 * t].y; rk[1] = rw[2 * t + 1].y;
#pragma unroll 1
            for (int it = 0; it < SPIN_MAX; it++) {
                uint32_t m = max(hv[20], hv[21]);
#pragma unroll
                for (int k = 0; k < 20; k += 2) m = __vimax3_u32(m, hv[k], hv[k + 1]);
                if (!__any_sync(~0u, m == ~0u)) break;
                ask();
            }
            if (wg && lane == 0) mbar_arrive(bars + 416);
            if (up0) rk[0] = __uint_as_float(hv[20]);
            if (up1) rk[1] = __uint_as_float(hv[21]);
#pragma unroll
            for (int j = 0; j < 10; j++) asm volatile("movmatrix.sync.aligned.m8n8.trans.b16 %0, %1;" : "=r"(vp[j]) : "r"(hv[j < 8 ? 12 + j : 2 + j]));
        };
        rk[2] = rw[2 * t + (up0 ? 0 : 8)].y; rk[3] = rw[2 * t + 1 + (up1 ? 0 : 8)].y;
        uint32_t qs[4][2];
#pragma unroll
        for (int h = 0; h < 4; h++) {
            qs[h][0] = (t >> 1) == (h & 1) ? f[0][5 * (h >> 1) + 2] : 0u; qs[h][1] = (t >> 1) == (h & 1) ? f[1][5 * (h >> 1) + 2] : 0u;
            asm volatile("" : "+r"(qs[h][0]), "+r"(qs[h][1]));
        }
#pragma unroll
        for (int j = 0; j < 10; j++) asm volatile("" : "+r"(f[0][j]), "+r"(f[1][j]), "+r"(f[0][10 + j]));
        if (warp & 3) above(); else if (wg) ask(); else hv[20] = mb ? ~0u : 0u;
        TSTAMP1T(10, 64); CSA(2);
        if (warp && !wg) mbar_wait(bars + 416 + 8 * warp, 0);
        CSA(3);
        float sc[4][3][4];
#pragma unroll
        for (int h = 0; h < 4; h++) {
            const int jb = 5 * (h >> 1) + 3 * (h & 1), js = 5 * (h >> 1) + 2;
#pragma unroll
            for (int nt = 1; nt < 3; nt++) {
#pragma unroll
                for (int e = 0; e < 4; e++) sc[h][nt][e] = 0.f;
                mma_bf16(sc[h][nt], f[0][jb], f[1][jb], f[0][jb + 1], f[1][jb + 1], f[nt - 1][10 + jb], f[nt - 1][11 + jb]);
                mma_bf16_k8(sc[h][nt], qs[h][0], qs[h][1], f[nt - 1][10 + js]);
            }
        }
        if (!(warp & 3)) halo();
        TSTAMP1(8); CSA(4);
#pragma unroll
        for (int h = 0; h < 4; h++) {
            const int jb = 5 * (h >> 1) + 3 * (h & 1), js = 5 * (h >> 1) + 2;
#pragma unroll
            for (int e = 0; e < 4; e++) sc[h][0][e] = 0.f;
            mma_bf16(sc[h][0], f[0][jb], f[1][jb], f[0][jb + 1], f[1][jb + 1], kp[jb], kp[jb + 1]);
            mma_bf16_k8(sc[h][0], qs[h][0], qs[h][1], kp[js]);
        }
        TSTAMP1T(3, 64);
        float p[4][4], sum[4][2];
        uint32_t lg[4][2], mx[4];
        const float rl[4] = {rk[0] * ra, rk[1] * ra, rk[2] * rb, rk[3] * rb};
        auto max2 = [](uint32_t a, uint32_t b) { uint32_t r; asm("max.bf16x2 %0, %1, %2;" : "=r"(r) : "r"(a), "r"(b)); return r; };
#pragma unroll
        for (int h = 0; h < 4; h++) {
            lg[h][0] = pack2((up0 ? sc[h][0][0] : sc[h][1][0]) * rl[0], (up0 ? sc[h][1][2] : sc[h][2][2]) * rl[2]);
            lg[h][1] = pack2((up1 ? sc[h][0][1] : sc[h][1][1]) * rl[1], (up1 ? sc[h][1][3] : sc[h][2][3]) * rl[3]);
            if (edge) {
                if (up0) lg[h][0] = __byte_perm(lg[h][0], 0xce6eu, 0x3254);
                if (up1) lg[h][1] = __byte_perm(lg[h][1], 0xce6eu, 0x3254);
            }
            mx[h] = max2(lg[h][0], lg[h][1]);
        }
#pragma unroll
        for (int o = 1; o <= 2; o <<= 1)
#pragma unroll
            for (int h = 0; h < 4; h++) mx[h] = max2(mx[h], __shfl_xor_sync(~0u, mx[h], o));
#pragma unroll
        for (int h = 0; h < 4; h++)
#pragma unroll
            for (int r = 0; r < 2; r++) {
                const float m = __uint_as_float(r ? mx[h] & 0xffff0000u : mx[h] << 16);
#pragma unroll
                for (int e = 0; e < 2; e++)
                    asm("ex2.approx.ftz.f32 %0, %1;" : "=f"(p[h][2 * r + e]) : "f"((__uint_as_float(r ? lg[h][e] & 0xffff0000u : lg[h][e] << 16) - m) * 1.4426950408889634f));
            }
#pragma unroll
        for (int h = 0; h < 4; h++) {
            float d0, d1;
            asm("{\n.reg .b32 a, b;\ncvt.rn.f16x2.f32 a, %5, %4;\ncvt.rn.f16x2.f32 b, %7, %6;\n"
                "mma.sync.aligned.m16n8k8.row.col.f32.f16.f16.f32 {%0,%1,%2,%3}, {a,b}, {%8}, {%9,%9,%9,%9};\n}"
                : "=f"(sum[h][0]), "=f"(d0), "=f"(sum[h][1]), "=f"(d1) : "f"(p[h][0]), "f"(p[h][1]), "f"(p[h][2]), "f"(p[h][3]), "r"(0x3c003c00u), "f"(0.f));
        }
        TSTAMP1T(5, 64); CSA(5);
        const uint32_t mu = (up0 ? 0xffffu : 0u) | (up1 ? 0xffff0000u : 0u);
        uint32_t ob[10][2];
#pragma unroll
        for (int P = 0; P < 2; P++) {
            float os[2][4];
#pragma unroll
            for (int e = 0; e < 2; e++) {
                const int h = 2 * P + e;
                const float i0 = rcp_apx(sum[h][0]), i1 = rcp_apx(sum[h][1]);
                const uint32_t w0 = pack2(p[h][0] * rk[0] * i0, p[h][1] * rk[1] * i0), w1 = pack2(p[h][2] * rk[2] * i1, p[h][3] * rk[3] * i1);
#pragma unroll
                for (int dt = 0; dt < 3; dt++) {
                    const int j = 5 * P + (dt < 2 ? 3 * e + dt : 2);
                    float o[4] = {0.f, 0.f, 0.f, 0.f};
                    mma_bf16(o, w0 & ~mu, w1 & mu, 0u, w1 & ~mu, vb[j][0], vb[j][1]);
                    mma_bf16_k8(o, w0 & mu, 0u, vp[j]);
                    if (dt < 2) { ob[j][0] = pack2(o[0], o[1]); ob[j][1] = pack2(o[2], o[3]); }
                    else { os[e][0] = o[0]; os[e][1] = o[1]; os[e][2] = o[2]; os[e][3] = o[3]; }
                }
            }
#pragma unroll
            for (int k = 0; k < 4; k++) os[0][k] = t < 2 ? os[0][k] : os[1][k];
            ob[5 * P + 2][0] = pack2(os[0][0], os[0][1]); ob[5 * P + 2][1] = pack2(os[0][2], os[0][3]);
        }
        const uint32_t sl = sbase + (wg ? A1_SM_A1 : A1_SM_A0);
        const uint32_t o0 = (warp & 3) * 2048 + g * 64 + ((t ^ (g >> 1)) << 4), o1 = 8192 + (warp & 3) * 512 + g * 32 + ((t ^ ((g >> 2) << 1)) << 3);
        CSA(15);
#pragma unroll
        for (int j = 0; j < 10; j++) asm volatile("" : "+r"(ob[j][0]), "+r"(ob[j][1]) :: "memory");
        if (wg == 0 && lane == 0) mbar_arrive(bar_pv);
        mbar_wait(bar_done, 0);
        if (wg == 0) mbar_wait(bar_kvf, 0);
#pragma unroll
        for (int h = 0; h < 2; h++) {
            asm volatile("st.shared.v4.u32 [%0], {%1,%2,%3,%4};" ::"r"(sl + o0 + h * 1024), "r"(ob[0][h]), "r"(ob[1][h]), "r"(ob[2][h]), "r"(ob[3][h]) : "memory");
            asm volatile("st.shared.v4.u32 [%0], {%1,%2,%3,%4};" ::"r"(sl + o0 + h * 1024 + 512), "r"(ob[4][h]), "r"(ob[5][h]), "r"(ob[6][h]), "r"(ob[7][h]) : "memory");
            asm volatile("st.shared.v2.u32 [%0], {%1,%2};" ::"r"(sl + o1 + h * 256), "r"(ob[8][h]), "r"(ob[9][h]) : "memory");
        }
        if (warp > 4 && lane == 0) mbar_arrive(bars + 384 + 8 * warp);
        fence_async_smem();
        __syncwarp();
        TSTAMP1T(4, 64); CSA(6);
        TSTAMP1(1);
        TSTAMP2(1);
        const unsigned char* ot = reinterpret_cast<const unsigned char*>(of) + mb * 163840 + wg * 10240;
        if (lane == 0) {
            asm volatile("cp.async.bulk.global.shared::cta.bulk_group [%0], [%1], 2048;" ::"l"(ot + hg * 20480 + (warp & 3) * 2048), "r"(sl + (warp & 3) * 2048) : "memory");
            asm volatile("cp.async.bulk.global.shared::cta.bulk_group [%0], [%1], 512;" ::"l"(ot + hg * 20480 + 8192 + (warp & 3) * 512), "r"(sl + 8192 + (warp & 3) * 512) : "memory");
            asm volatile("cp.async.bulk.commit_group;" ::: "memory");
            asm volatile("cp.async.bulk.wait_group 0;" ::: "memory");
            asm volatile(A1_FRED " [%0], 1;" ::"l"(reinterpret_cast<uint32_t*>(rsum + 2 * SEQ) + (((layer * 16 + mb) * 2 + wg) * 8 + hg) * FSTR) : "memory");
            DBGC(4 + warp);
        }
        TSTAMP4(11); CSA(7);
        float ac2[40];
        const uint64_t db0 = make_desc(sbase, 1024, 256, 3), db1 = make_desc(sbase + 10240, 512, 256, 3), da0 = make_desc(sl, 16, 1024, 2), da1 = make_desc(sl + 8192, 16, 256, 3);
        const uint32_t o7 = wg ? 640 : (A1_SM_W0 - A1_SM_A0) >> 4;
        const uint32_t trow = ((lane & 7) + 8 * (lane >> 4)) * 128 + (((2 * (warp & 3) + ((lane >> 3) & 1)) ^ (lane & 7)) << 4);
        uint32_t xr[10][2];
        mbar_wait(bar_f2 + 64 * wg + 64, 0);
        if (layer == 0) {
#pragma unroll
            for (int j = 0; j < 10; j += 2) ldsm_x4(&xr[j][0], sl + 51200 + (16 * (warp & 3) + (lane & 15)) * 160 + (lane >> 4) * 16 + 16 * j);
        } else {
#pragma unroll
            for (int j = 0; j < 10; j += 2) ldsm_x4_t(&xr[j][0], sl + 51200 + trow + 1024 * j);
        }
        const uint32_t ri = __shfl_sync(~0u, layer * SEQ + (wg * 2 + ((g >> 1) & 1)) * 512 + (mb * 16 + 4 * (warp & 3) + (g >> 2)) * 2 + (g & 1), lane);
        mbar_wait(bar_wo, 0);
        if (wg) asm volatile("bar.sync 2, 128;" ::: "memory"); else asm volatile("bar.sync 1, 128;" ::: "memory");
        if (wg) mbar_wait(bar_pv, 0);
        TSTAMP2(2); CSA(8);
#pragma unroll
        for (int q = 0; q < 8; q++) {
            uint32_t bo = wo_off(0) >> 4;
            if (q) {
                mbar_wait(bar_f2 + 64 * wg + 8 * q, 0);
                asm volatile("ld.shared.u32 %0, [%1];" : "=r"(bo) : "r"(que + 32 * wg + 4 * q) : "memory");
                bo = __shfl_sync(~0u, bo, 0);
                TSTAMP4(q);
                if (q % 3 == 1) CSA(9 + q / 3);
                if (q == 1 && (tid & 127) == 0) DBGC(29 + 8 * wg);
            }
            wgmma_fence();
#pragma unroll
            for (int j = 0; j < 5; j++) wgmma_n80(ac2, (j < 4 ? da0 : da1) + (q == 7 ? o7 : 0u) + (uint64_t)((q < 6 ? q * 640 : 0) + (j & 2) * 16 + (j & 1) * 2), (j < 4 ? db0 : db1) + bo + (uint64_t)((j & 2) * 160 + (j & 1) * 32), j || q);
            wgmma_commit();
            if (q == 0) {
                wgmma_wait<0>();
                if ((tid & 127) == 0) { mbar_arrive(bar_e2 + 16 * wg); mbar_arrive(bar_e2 + 8); }
            }
            if (q == 2 && wg) {
                wgmma_wait<1>();
                if (tid == 128) mbar_arrive(bar_e2 + 24);
            }
        }
        if ((tid & 127) == 0) DBGC(28 + wg * 8 + 7);
        TSTAMP2(3);
        wgmma_wait<0>();
        TSTAMP2(4); CSA(12);
        if (__any_sync(~0u, ac2[0] != ac2[0] || ac2[2] != ac2[2])) {
#pragma unroll
            for (int i = 0; i < 40; i++) ac2[i] = 0.f;
            uint32_t a[20], an[20];
            auto lda = [&](uint32_t (&r)[20], int h) {
#pragma unroll
                for (int u = 0; u < 4; u++)
                    asm volatile("ld.relaxed.gpu.global.v4.u32 {%0,%1,%2,%3}, [%4];" : "=r"(r[4 * u]), "=r"(r[4 * u + 1]), "=r"(r[4 * u + 2]), "=r"(r[4 * u + 3]) : "l"(ot + h * 20480 + o0 + u * 512) : "memory");
#pragma unroll
                for (int u = 0; u < 2; u++)
                    asm volatile("ld.relaxed.gpu.global.v2.u32 {%0,%1}, [%2];" : "=r"(r[16 + 2 * u]), "=r"(r[17 + 2 * u]) : "l"(ot + h * 20480 + o1 + u * 256) : "memory");
            };
            lda(an, 0);
#pragma unroll 5
            for (int k = lane; k < WOB / 16; k += 32)
                reinterpret_cast<uint4*>(stg + (sl - sbase))[k] = __ldcg(reinterpret_cast<const uint4*>(wo + hg * 8 * WOB) + k);
            __syncwarp();
#pragma unroll 1
            for (int h = 0; h < 8; h++) {
#pragma unroll 1
                for (int it = 0; it < SPIN_MAX; it++) {
                    uint32_t m = 0;
#pragma unroll
                    for (int k = 0; k < 20; k += 2) m = __vimax3_u32(m, an[k], an[k + 1]);
                    if (!__any_sync(~0u, m == ~0u)) break;
                    lda(an, h);
                }
#pragma unroll
                for (int k = 0; k < 20; k++) a[k] = an[k];
                lda(an, min(h + 1, 7));
                const uint32_t bp = h == hg ? sl : sbase + wo_off(h + (h < hg));
                const int r0 = 8 * ((lane & 7) >> 1) + 2 * (lane >> 3) + (lane & 1), r2 = 4 * ((lane & 7) >> 1) + 2 * ((lane >> 3) & 1) + (lane & 1);
#pragma unroll
                for (int n = 0; n < 10; n++) {
                    uint32_t b[12];
                    ldsm_x4_t(b, bp + (n >> 1) * 1024 + r0 * 32 + (((n ^ (r0 >> 2)) & 1) << 4));
                    ldsm_x4_t(b + 4, bp + 5120 + (n >> 1) * 1024 + r0 * 32 + (((n ^ (r0 >> 2)) & 1) << 4));
                    ldsm_x4_t(b + 8, bp + 10240 + (n >> 1) * 512 + r2 * 32 + (((n ^ (r2 >> 2)) & 1) << 4));
                    mma_bf16(ac2 + 4 * n, a[0], a[8], a[1], a[9], b[0], b[1]); mma_bf16(ac2 + 4 * n, a[2], a[10], a[3], a[11], b[2], b[3]);
                    mma_bf16(ac2 + 4 * n, a[4], a[12], a[5], a[13], b[4], b[5]); mma_bf16(ac2 + 4 * n, a[6], a[14], a[7], a[15], b[6], b[7]);
                    mma_bf16(ac2 + 4 * n, a[16], a[18], a[17], a[19], b[8], b[9]);
                }
            }
        }
#pragma unroll
        for (int j = 0; j < 10; j++)
#pragma unroll
            for (int hh = 0; hh < 2; hh++) {
                const uint32_t a = pack2(ac2[4 * j + 2 * hh], ac2[4 * j + 2 * hh + 1]);
                const __nv_bfloat162 r = __hadd2_rn(*reinterpret_cast<const __nv_bfloat162*>(&xr[j][hh]), *reinterpret_cast<const __nv_bfloat162*>(&a));
                xr[j][hh] = *reinterpret_cast<const uint32_t*>(&r);
            }
        const uint32_t so = sl + 30720;
#pragma unroll
        for (int j = 0; j < 10; j += 2) stsm_x4_t(so + trow + 1024 * j, xr[j][0], xr[j][1], xr[j + 1][0], xr[j + 1][1]);
        if (wg) asm volatile("bar.sync 2, 128;" ::: "memory"); else asm volatile("bar.sync 1, 128;" ::: "memory");
        TSTAMP2(5); CSA(13);
        if ((tid & 127) == 0) {
            fence_async_smem();
            asm volatile("cp.async.bulk.tensor.2d.global.shared::cta.bulk_group [%0, {%1, %2}], [%3];" ::"l"(&tmX1), "r"(mb * 128 + 64 * wg), "r"(hg * 80), "r"(so) : "memory");
            asm volatile("cp.async.bulk.commit_group;" ::: "memory");
        }
        __syncwarp();
        const float p0 = *(volatile const float*)&rw[g].x, p1 = *(volatile const float*)&rw[g + 8].x;
        float s[3][4] = {};
        const uint32_t pp[2] = {__byte_perm(__float_as_uint(p0), 0, 0x3232), __byte_perm(__float_as_uint(p1), 0, 0x3232)};
#pragma unroll
        for (int j = 0; j < 10; j += 2) {
            const uint32_t d0 = sub2(xr[j][0], pp[0]), d1 = sub2(xr[j][1], pp[1]), d2 = sub2(xr[j + 1][0], pp[0]), d3 = sub2(xr[j + 1][1], pp[1]);
            mma_bf16(s[0], xr[j][0], xr[j][1], xr[j + 1][0], xr[j + 1][1], 0x3f803f80u, 0x3f803f80u);
            mma_bf16(s[1], d0, d1, d2, d3, d0, d2);
            mma_bf16(s[2], d0, d1, d2, d3, d1, d3);
        }
        if (t == (g >> 1)) {
            float2* rp = rsum + ri;
            constexpr float idm = 1.0f / DM;
            asm volatile("red.relaxed.gpu.global.add.v2.f32 [%0], {%1, %2};" ::"l"(rp), "f"(fmaf(-80.f, p0, s[0][0]) * idm), "f"(((g & 1) ? s[1][1] : s[1][0]) * idm) : "memory");
            asm volatile("red.relaxed.gpu.global.add.v2.f32 [%0], {%1, %2};" ::"l"(rp + 4), "f"(fmaf(-80.f, p1, s[0][2]) * idm), "f"(((g & 1) ? s[2][3] : s[2][2]) * idm) : "memory");
        }
        asm volatile("cp.async.bulk.wait_group.read 0;" ::: "memory");
        TSTAMP2(6); CSA(14); CSA_END;
        if (tid == 0) DBGC(63);
        if (tid == 128) DBGC(28);
        if (tid == 0) DBGCAL(2);
        GSTAMP(g_tim1, 14);
        SPAN(1 + 4 * layer, 3);
    }
#undef layer
}

static int h_nsm;
static void* h_sym[11];
static TileTab h_tab[2];
static CUtensorMap h_tmX0, h_tmX1, h_tmR0, h_tmR1, h_tmX1st, h_tmOut;
static KgMaps h_tmW;
typedef CUresult (*PFN_encodeTiled)(CUtensorMap*, CUtensorMapDataType, cuuint32_t, void*, const cuuint64_t*, const cuuint64_t*,
                                    const cuuint32_t*, const cuuint32_t*, CUtensorMapInterleave, CUtensorMapSwizzle,
                                    CUtensorMapL2promotion, CUtensorMapFloatOOBfill);
static void make_tmap(CUtensorMap* tm, const void* ptr, uint64_t cols, uint64_t rows, uint32_t bc, uint32_t br, CUtensorMapSwizzle sw, uint64_t pitch = 0, uint64_t hi = 0, uint32_t bh = 2) {
    static PFN_encodeTiled fn = nullptr;
    if (!fn) {
        void* p = nullptr; cudaDriverEntryPointQueryResult qr;
        cudaGetDriverEntryPoint("cuTensorMapEncodeTiled", &p, cudaEnableDefault, &qr);
        fn = (PFN_encodeTiled)p;
    }
    if (br == 0) {
        cuuint64_t dims[5] = {16, 2, rows / 8, 4, cols / 16}; cuuint64_t strides[4] = {cols * 2, cols * 16, cols * 4, 32};
        cuuint32_t box[5] = {16, 2, bc, 4, 5}; cuuint32_t es[5] = {1, 1, 1, 1, 1};
        fn(tm, CU_TENSOR_MAP_DATA_TYPE_BFLOAT16, 5, const_cast<void*>(ptr), dims, strides, box, es, CU_TENSOR_MAP_INTERLEAVE_NONE, sw,
           CU_TENSOR_MAP_L2_PROMOTION_L2_128B, CU_TENSOR_MAP_FLOAT_OOB_FILL_NONE);
        return;
    }
    if (hi == 16) {
        cuuint64_t dims[4] = {16, 32, 120, 20}; cuuint64_t strides[3] = {3840, 32, 32 * 3840};
        cuuint32_t box[4] = {16, 32, 5, 2}; cuuint32_t es[4] = {1, 1, 1, 1};
        fn(tm, CU_TENSOR_MAP_DATA_TYPE_BFLOAT16, 4, const_cast<void*>(ptr), dims, strides, box, es, CU_TENSOR_MAP_INTERLEAVE_NONE, sw,
           CU_TENSOR_MAP_L2_PROMOTION_L2_128B, CU_TENSOR_MAP_FLOAT_OOB_FILL_NONE);
        return;
    }
    if (bh == 0) {
        cuuint64_t dims[5] = {64, 64, 2, 16, 10}; cuuint64_t strides[4] = {pitch * 2, hi * 2, cols * 2, rows * 2};
        cuuint32_t box[5] = {64, 64, 2, 1, 1}; cuuint32_t es[5] = {1, 1, 1, 1, 1};
        fn(tm, CU_TENSOR_MAP_DATA_TYPE_BFLOAT16, 5, const_cast<void*>(ptr), dims, strides, box, es, CU_TENSOR_MAP_INTERLEAVE_NONE, sw,
           CU_TENSOR_MAP_L2_PROMOTION_L2_128B, CU_TENSOR_MAP_FLOAT_OOB_FILL_NONE);
        return;
    }
    if (hi) {
        cuuint64_t dims[3] = {cols, rows, hi == 64 ? 32u : 2u}; cuuint64_t strides[2] = {pitch * 2, hi * 2};
        cuuint32_t box[3] = {bc, br, bh}; cuuint32_t es[3] = {1, 1, 1};
        fn(tm, CU_TENSOR_MAP_DATA_TYPE_BFLOAT16, 3, const_cast<void*>(ptr), dims, strides, box, es, CU_TENSOR_MAP_INTERLEAVE_NONE, sw,
           CU_TENSOR_MAP_L2_PROMOTION_L2_128B, CU_TENSOR_MAP_FLOAT_OOB_FILL_NONE);
        return;
    }
    cuuint64_t dims[2] = {cols, rows}; cuuint64_t strides[1] = {(pitch ? pitch : cols) * 2};
    cuuint32_t box[2] = {bc, br}; cuuint32_t es[2] = {1, 1};
    fn(tm, CU_TENSOR_MAP_DATA_TYPE_BFLOAT16, 2, const_cast<void*>(ptr), dims, strides, box, es, CU_TENSOR_MAP_INTERLEAVE_NONE, sw,
       CU_TENSOR_MAP_L2_PROMOTION_L2_128B, CU_TENSOR_MAP_FLOAT_OOB_FILL_NONE);
}
template <typename... Args>
static void launch_pdl(void (*kern)(Args...), int grid, int block, int smem, Args... args) {
    cudaLaunchConfig_t cfg = {};
    cfg.gridDim = dim3(grid); cfg.blockDim = dim3(block); cfg.dynamicSmemBytes = smem; cfg.stream = cudaStreamPerThread;
    cudaLaunchAttribute at[1];
    at[0].id = cudaLaunchAttributeProgrammaticStreamSerialization; at[0].val.programmaticStreamSerializationAllowed = 1;
    cfg.attrs = at; cfg.numAttrs = 1;
    cudaLaunchKernelEx(&cfg, kern, args...);
}
static void launch_stage(int k, void* const* d_in, void* d_out) {
    const Par par = {k > 1 ? nullptr : (const bf16*)d_in[4], (const bf16*)d_in[5], (const bf16*)d_in[6], (const bf16*)d_in[7], (const bf16*)d_in[8], (const bf16*)d_in[9], k > 1, 0, (const bf16*)d_in[0],
                     (uint4*)h_sym[4], (uint4*)h_sym[2], (uint4*)h_sym[6], (uint4*)h_sym[3], (uint4*)h_sym[0], (float*)h_sym[5], (uint4*)h_sym[1], (const bf16*)d_in[1], (const bf16*)d_in[2]};
    auto a1 = h_nsm == 132 ? a1_kernel<true> : a1_kernel<false>;
    switch (k) {
        case 1: a1<<<h_nsm, A1_THREADS, A1_SMEM, cudaStreamPerThread>>>(par, h_tmX0, h_tmR0, h_tmX1st, h_tmW, h_tab[0]); break;
        case 3: launch_pdl(conv_kernel, DM / CV_CPB, CV_THREADS, CV_SMEM, 0, (const uint4*)h_sym[7], (const float4*)h_sym[4], (const bf16*)h_sym[8], (bf16*)h_sym[9], (const uint4*)h_sym[0], h_tmOut); break;
        case 5: launch_pdl(a1, h_nsm, A1_THREADS, A1_SMEM, par, h_tmX1, h_tmR1, h_tmX1st, h_tmW, h_tab[1]); break;
        case 7: launch_pdl(conv_kernel, DM / CV_CPB, CV_THREADS, CV_SMEM, 1, (const uint4*)h_sym[7] + SEQ / 8, (const float4*)h_sym[4] + SEQ / 2, (const bf16*)h_sym[8], (bf16*)h_sym[10], (const uint4*)h_sym[0], h_tmOut); break;
        default: break;
    }
}
static int n_stage_kernels() { return 9; }
static const char* stage_name(int k) { const char* n[] = {"kgen", "a1", "a2", "conv", "tr", "a1", "a2", "conv", "tr"}; return n[k]; }

extern "C" void kernel_launch(void* const* d_in, const int* in_sizes, int n_in, void* d_out, int out_size) {
    (void)in_sizes; (void)n_in; (void)out_size;
    static const void *p_in = nullptr, *p_w1 = nullptr, *p_w2 = nullptr, *p_out = nullptr;
    if (p_in != d_in[0] || p_w1 != d_in[1] || p_w2 != d_in[2] || p_out != d_out) {
        cudaFuncSetAttribute(conv_kernel, cudaFuncAttributeMaxDynamicSharedMemorySize, CV_SMEM);
        cudaFuncSetAttribute(a1_kernel<true>, cudaFuncAttributeMaxDynamicSharedMemorySize, A1_SMEM);
        cudaFuncSetAttribute(a1_kernel<false>, cudaFuncAttributeMaxDynamicSharedMemorySize, A1_SMEM);
        int dev; cudaGetDevice(&dev); cudaDeviceGetAttribute(&h_nsm, cudaDevAttrMultiProcessorCount, dev);
        if (h_nsm != 132) h_nsm = 128;
        cudaGetSymbolAddress(&h_sym[0], g_tap); cudaGetSymbolAddress(&h_sym[1], g_wq); cudaGetSymbolAddress(&h_sym[2], g_wo);
        cudaGetSymbolAddress(&h_sym[3], g_halo); cudaGetSymbolAddress(&h_sym[4], g_sum); cudaGetSymbolAddress(&h_sym[5], g_csp); cudaGetSymbolAddress(&h_sym[6], g_of);
        cudaGetSymbolAddress(&h_sym[7], g_piv); cudaGetSymbolAddress(&h_sym[8], g_x1T); cudaGetSymbolAddress(&h_sym[9], g_xcT); cudaGetSymbolAddress(&h_sym[10], g_yT);
        for (int i = 0; i < 264; i++) {
            const int s = i % 132, h = (s - 64) >> 1;
            const int t = h_nsm != 132 ? s : s < 64 ? ((s >> 1) & 7) * 16 + (s >> 4) * 2 + (s & 1) : s < 120 ? (1 + h % 7) * 16 + 8 + (h / 7) * 2 + (s & 1) : s < 124 ? 128 : s - 116;
            const int hg = (4 * (t >> 6) + (t & 3)) & 7;
            const uint64_t wp = (uint64_t)h_sym[1] + hg * 10 * WQ_STAGE;
            h_tab[i / 132].e[s] = make_uint4((uint32_t)wp, (uint32_t)(wp >> 32), ((t >> 2) & 15) | (i / 132) << 4 | hg << 8 | 5 * (hg >> 2) << 16 | (uint32_t)t << 24, 0);
        }
        void *px1, *px2;
        cudaGetSymbolAddress(&px1, g_x1T); cudaGetSymbolAddress(&px2, g_xcT);
        make_tmap(&h_tmX0, d_in[0], 128 * 640, 64, 64, 64, CU_TENSOR_MAP_SWIZZLE_128B, 1280, 640, 0);
        make_tmap(&h_tmX1, px2, 128, 64 * XCP, 64, 64, CU_TENSOR_MAP_SWIZZLE_128B, XCP, 64, 0);
        make_tmap(&h_tmR0, d_in[0], 640, 1024, 80, 64, CU_TENSOR_MAP_SWIZZLE_NONE, 1280, 640, 1);
        make_tmap(&h_tmR1, px2, 64, 640, 64, 80, CU_TENSOR_MAP_SWIZZLE_128B, XCP, 64, 1);
        make_tmap(&h_tmX1st, px1, 2048, 640, 64, 80, CU_TENSOR_MAP_SWIZZLE_128B, XCP);
        make_tmap(&h_tmW.q, d_in[1], 16, 640, 16, 32, CU_TENSOR_MAP_SWIZZLE_32B, 1920, 16, 5);
        make_tmap(&h_tmW.o, d_in[2], 640, 640, 4, 0, CU_TENSOR_MAP_SWIZZLE_32B);
        make_tmap(&h_tmW.t, d_in[2], 640, 640, 2, 0, CU_TENSOR_MAP_SWIZZLE_32B);
        make_tmap(&h_tmOut, d_out, 640, 1024, 80, 8, CU_TENSOR_MAP_SWIZZLE_NONE, 1280, 640, 1);
        p_in = d_in[0]; p_w1 = d_in[1]; p_w2 = d_in[2]; p_out = d_out;
    }
    for (int k = 0; k < n_stage_kernels(); k++) launch_stage(k, d_in, d_out);
}
```
